```python
import torch

def _softmax(x, axis=-1):
    return torch.softmax(x, dim=axis)
def _gelu(x):
    return torch.nn.functional.gelu(x, approximate="tanh")
def _silu(x):
    return torch.nn.functional.silu(x)
def _sigmoid(x):
    return torch.sigmoid(x)
def _layernorm(x, axis=-1, eps=1e-5):
    m = x.mean(dim=axis, keepdim=True)
    v = x.var(dim=axis, keepdim=True, unbiased=False)
    return (x - m) / torch.sqrt(v + eps)
def _scatter_add(tgt, idx, src, axis=0):
    return tgt.clone().index_add_(axis, idx, src)
def _segment_sum(src, seg, n):
    out = torch.zeros((n,) + src.shape[1:], dtype=src.dtype)
    return out.index_add_(0, seg, src)
def _pad(x, pw):
    flat = tuple(v for pair in reversed(pw) for v in pair)
    return torch.nn.functional.pad(x, flat)

kernel_name = 'concat_heads__linear_kernel_hedgehog__ssm_conv_s4d__prompt'

def setup_inputs():

    _w = (lambda a: (lambda t: t.to(torch.bfloat16) if t.is_floating_point() else t)(torch.as_tensor(a)))
    def _A_setup():
        B, S, D, H = 1, 2048, 512, 32
        Dh = D // H
        return {
            "x": _w((lambda *s: torch.randn(*s, dtype=torch.bfloat16) * 0.4)(B, S, D)),
            "wqkv": _w((lambda *s: torch.randn(*s, dtype=torch.bfloat16) * 0.4)(D, 3 * D)),
            "w_phi": _w((lambda *s: torch.randn(*s, dtype=torch.bfloat16) * 0.4)(H, Dh, Dh) * (Dh ** -0.5)),
            "wo": _w((lambda *s: torch.randn(*s, dtype=torch.bfloat16) * 0.05)(D, D)),
        }
    _A_in = _A_setup()

    def _B_setup():
        Bsz, L, D, N = 1, 2048, 512, 128
        return {
            "u": _w((lambda *s: torch.randn(*s, dtype=torch.bfloat16) * 0.05)(Bsz, L, D)),
            "log_A_real": _w((lambda *s: torch.randn(*s, dtype=torch.bfloat16) * 3.2)(D, N) * 0.5),
            "A_imag": _w((lambda *s: torch.randn(*s, dtype=torch.bfloat16) * 0.2)(D, N) * 3.14),
            "C_real": _w((lambda *s: torch.randn(*s, dtype=torch.bfloat16) * 3.2)(D, N) / N ** 0.5),
            "C_imag": _w((lambda *s: torch.randn(*s, dtype=torch.bfloat16) * 3.2)(D, N) / N ** 0.5),
            "log_dt": _w((lambda *s: torch.randn(*s, dtype=torch.bfloat16) * 0.2)(D) * 0.5 - 4.0),
            "D_skip": _w((lambda *s: torch.randn(*s, dtype=torch.bfloat16) * 0.4)(D)),
        }
    _B_in = _B_setup()

    return {
        "A_x": _A_in["x"],
        "A_wqkv": _A_in["wqkv"],
        "A_w_phi": _A_in["w_phi"],
        "A_wo": _A_in["wo"],
        "B_u": _B_in["u"],
        "B_log_A_real": _B_in["log_A_real"],
        "B_A_imag": _B_in["A_imag"],
        "B_C_real": _B_in["C_real"],
        "B_C_imag": _B_in["C_imag"],
        "B_log_dt": _B_in["log_dt"],
        "B_D_skip": _B_in["D_skip"],
    }

def reference(A_x, A_wqkv, A_w_phi, A_wo, B_u, B_log_A_real, B_A_imag, B_C_real, B_C_imag, B_log_dt, B_D_skip):
    def _A_ref(x, wqkv, w_phi, wo):
        B, S, D = x.shape
        H = 32; Dh = D // H
        qkv = (lambda x, *d: x.permute(*d))((x @ wqkv).reshape(B, S, 3, H, Dh), 2, 0, 3, 1, 4)
        q, k, v = qkv[0], qkv[1], qkv[2]
        pq = torch.einsum("bhsd,hdf->bhsf", q, w_phi)
        pk = torch.einsum("bhsd,hdf->bhsf", k, w_phi)
        phi_q = torch.concatenate([_softmax(pq, axis=-1), _softmax(-pq, axis=-1)], axis=-1)
        phi_k = torch.concatenate([_softmax(pk, axis=-1), _softmax(-pk, axis=-1)], axis=-1)
        kv = torch.einsum("bhsf,bhsd->bhfd", phi_k, v)
        z  = torch.einsum("bhsf->bhf", phi_k)
        num = torch.einsum("bhqf,bhfd->bhqd", phi_q, kv)
        den = torch.einsum("bhqf,bhf->bhq", phi_q, z)[..., None] + 1e-6
        o = num / den
        return (lambda x, *d: x.permute(*d))(o, 0, 2, 1, 3).reshape(B, S, D) @ wo

    def _B_ref(u, log_A_real, A_imag, C_real, C_imag, log_dt, D_skip):
        L = u.shape[1]
        dt = torch.exp(log_dt)
        A = -torch.exp(log_A_real) + 1j * A_imag
        C = (C_real + 1j * C_imag) * dt[:, None]
        pos = (lambda x, dt: x.to(dt))(torch.arange(L), log_dt.dtype)
        P = torch.exp((A * dt[:, None])[:, :, None] * pos[None, None, :])
        K = 2.0 * torch.einsum("dn,dnl->dl", C, P).real
        L2 = 2 * L
        u_t = (lambda x, *d: x.permute(*d))(u, 0, 2, 1)
        Kf = (lambda x, *a, **k: torch.fft.rfft(x.float(), *a, **k))(K, L2)
        Uf = (lambda x, *a, **k: torch.fft.rfft(x.float(), *a, **k))(u_t, L2)
        y = (lambda x, *a, **k: torch.fft.irfft(x, *a, **k).to(torch.bfloat16))(Uf * Kf[None, :, :], L2)[:, :, :L]
        y = (lambda x, *d: x.permute(*d))(y, 0, 2, 1)
        return y + u * D_skip[None, None, :]

    a = _A_ref(A_x, A_wqkv, A_w_phi, A_wo)
    b = _B_ref(B_u, B_log_A_real, B_A_imag, B_C_real, B_C_imag, B_log_dt, B_D_skip)
    return torch.concatenate([a, b], axis=-1)
```

```cpp
#include <cuda_runtime.h>
#include <cuda_bf16.h>
#include <cuda.h>
#include <stdint.h>

#define DBG_TS 0

namespace {

constexpr int NTHREADS = 512;
constexpr int NCTA = 128;
constexpr int OFF_W = 0;
constexpr int OFF_X = 98304;
constexpr int OFF_STG0 = 163840;
constexpr int OFF_U = 188416;
constexpr int U_CH = 4416, U_ODD = 2240, U_PAD = 128;
constexpr int OFF_T = OFF_U + 4 * U_CH;
constexpr int T_CH = 4864;
constexpr int T_D = 0;
constexpr int T_5 = 2144;
constexpr int T_3 = T_5 + 384;
constexpr int T_7 = T_3 + 384;
constexpr int T_9 = T_7 + 320;
constexpr int T_KC = T_9 + 320;
constexpr int OFF_BAR = OFF_T + 4 * T_CH;
constexpr int SMEM_BYTES = OFF_BAR + 256 + 1024;
static_assert(T_KC + 2 * 656 <= T_CH, "table size");
static_assert(SMEM_BYTES <= 232448, "smem");
constexpr int MB_WFULL = 0, MB_XFULL = 8, MB_XEMPTY = 12, MB_WOFULL = 16, MB_UFULL = 24, MB_GDONE = 25;
constexpr int NB_WG0 = 1, NB_OPEN = 2, NB_CLOSE = 3, NB_KPART = 4, NB_ST0 = 5, NB_ST1 = 6, NB_KV = 7,
              NB_BDONE = 8, NB_RED = 9, NB_INIT = 10;
constexpr int SPIN_MAX = 1 << 18;

__device__ unsigned g_cnt;
__device__ uint4 g_uT[512 * 256];
__device__ uint4 g_part[16 * 8 * 256];
__device__ uint4 g_z[16 * 8 * 16];
__device__ uint4 g_o[32 * 32 * 128];
__device__ uint4 g_y[512 * 8 * 32];
#define TS(i) do {} while (0)

__device__ __forceinline__ uint32_t smem_u32(const void* p) { return (uint32_t)__cvta_generic_to_shared(p); }
__device__ __forceinline__ void mbar_init(uint32_t b, int n) {
  asm volatile("mbarrier.init.shared::cta.b64 [%0], %1;" ::"r"(b), "r"(n) : "memory");
}
__device__ __forceinline__ void mbar_expect(uint32_t b, int bytes) {
  asm volatile("mbarrier.arrive.expect_tx.shared::cta.b64 _, [%0], %1;" ::"r"(b), "r"(bytes) : "memory");
}
__device__ __forceinline__ void mbar_arrive(uint32_t b) {
  asm volatile("mbarrier.arrive.shared::cta.b64 _, [%0];" ::"r"(b) : "memory");
}
__device__ __forceinline__ void mbar_wait(uint32_t b, uint32_t parity) {
  uint32_t done = 0;
  for (int i = 0; i < SPIN_MAX && !done; i++) {
    asm volatile("{\n.reg .pred p;\nmbarrier.try_wait.parity.shared::cta.b64 p, [%1], %2;\nselp.u32 %0, 1, 0, p;\n}\n"
                 : "=r"(done) : "r"(b), "r"(parity) : "memory");
  }
}
__device__ __forceinline__ void nb_sync(int id, int n) { asm volatile("bar.sync %0, %1;" ::"r"(id), "r"(n) : "memory"); }
__device__ __forceinline__ void nb_arrive(int id, int n) { asm volatile("bar.arrive %0, %1;" ::"r"(id), "r"(n) : "memory"); }
__device__ __forceinline__ void tma2d(uint32_t dst, const CUtensorMap* m, uint32_t bar, int c0, int c1) {
  asm volatile("cp.async.bulk.tensor.2d.shared::cluster.global.mbarrier::complete_tx::bytes [%0], [%1, {%3,%4}], [%2];"
               ::"r"(dst), "l"(m), "r"(bar), "r"(c0), "r"(c1) : "memory");
}
__device__ __forceinline__ void tma3d(uint32_t dst, const CUtensorMap* m, uint32_t bar, int c0, int c1, int c2) {
  asm volatile("cp.async.bulk.tensor.3d.shared::cluster.global.mbarrier::complete_tx::bytes [%0], [%1, {%3,%4,%5}], [%2];"
               ::"r"(dst), "l"(m), "r"(bar), "r"(c0), "r"(c1), "r"(c2) : "memory");
}
__device__ __forceinline__ void bulk_g2s(uint32_t dst, const void* src, int bytes, uint32_t bar) {
  asm volatile("cp.async.bulk.shared::cluster.global.mbarrier::complete_tx::bytes [%0], [%1], %2, [%3];"
               ::"r"(dst), "l"(src), "r"(bytes), "r"(bar) : "memory");
}
__device__ __forceinline__ void l2_prefetch(const void* p, int bytes) {
  asm volatile("cp.async.bulk.prefetch.L2.global [%0], %1;" ::"l"(p), "r"(bytes) : "memory");
}
__device__ __forceinline__ uint64_t mkdesc(uint32_t addr, uint32_t lbo, uint32_t sbo, int swz) {
  return (uint64_t)((addr & 0x3FFFF) >> 4) | ((uint64_t)(lbo >> 4) << 16) | ((uint64_t)(sbo >> 4) << 32) |
         ((uint64_t)swz << 62);
}
#define WG_FENCE() asm volatile("wgmma.fence.sync.aligned;" ::: "memory")
#define WG_COMMIT() asm volatile("wgmma.commit_group.sync.aligned;" ::: "memory")
#define WG_WAIT(n) asm volatile("wgmma.wait_group.sync.aligned " #n ";" ::: "memory")

__device__ __forceinline__ void mma(float& d0, float& d1, float& d2, float& d3, uint32_t a0, uint32_t a1, uint32_t a2,
                                    uint32_t a3, uint32_t b0, uint32_t b1) {
  asm volatile("mma.sync.aligned.m16n8k16.row.col.f32.bf16.bf16.f32 {%0,%1,%2,%3},{%4,%5,%6,%7},{%8,%9},{%0,%1,%2,%3};"
               : "+f"(d0), "+f"(d1), "+f"(d2), "+f"(d3)
               : "r"(a0), "r"(a1), "r"(a2), "r"(a3), "r"(b0), "r"(b1));
}
__device__ __forceinline__ void mma0(float& d0, float& d1, float& d2, float& d3, uint32_t a0, uint32_t a1, uint32_t a2,
                                     uint32_t a3, uint32_t b0, uint32_t b1) {
  asm volatile("mma.sync.aligned.m16n8k16.row.col.f32.bf16.bf16.f32 {%0,%1,%2,%3},{%4,%5,%6,%7},{%8,%9},{%10,%10,%10,%10};"
               : "=f"(d0), "=f"(d1), "=f"(d2), "=f"(d3)
               : "r"(a0), "r"(a1), "r"(a2), "r"(a3), "r"(b0), "r"(b1), "f"(0.f));
}
__device__ __forceinline__ uint32_t pack_bf(float lo, float hi) {
  uint32_t r;
  asm("cvt.rn.bf16x2.f32 %0, %1, %2;" : "=r"(r) : "f"(hi), "f"(lo));
  return r;
}
__device__ __forceinline__ float bf_lo(uint32_t w) { return __uint_as_float(w << 16); }
__device__ __forceinline__ float bf_hi(uint32_t w) { return __uint_as_float(w & 0xffff0000u); }
__device__ __forceinline__ float bf_round(float x) { return __bfloat162float(__float2bfloat16_rn(x)); }
__device__ __forceinline__ uint32_t bmax2(uint32_t a, uint32_t b) {
  uint32_t r; asm("max.bf16x2 %0, %1, %2;" : "=r"(r) : "r"(a), "r"(b)); return r;
}
__device__ __forceinline__ uint32_t bmin2(uint32_t a, uint32_t b) {
  uint32_t r; asm("min.bf16x2 %0, %1, %2;" : "=r"(r) : "r"(a), "r"(b)); return r;
}
__device__ __forceinline__ float ex2(float x) { float r; asm("ex2.approx.ftz.f32 %0, %1;" : "=f"(r) : "f"(x)); return r; }
__device__ __forceinline__ float rcp(float x) { float r; asm("rcp.approx.ftz.f32 %0, %1;" : "=f"(r) : "f"(x)); return r; }
__device__ __forceinline__ void ldsm4(uint32_t (&r)[4], uint32_t a) {
  asm volatile("ldmatrix.sync.aligned.m8n8.x4.shared.b16 {%0,%1,%2,%3}, [%4];"
               : "=r"(r[0]), "=r"(r[1]), "=r"(r[2]), "=r"(r[3]) : "r"(a) : "memory");
}
__device__ __forceinline__ void ldsm4t(uint32_t (&r)[4], uint32_t a) {
  asm volatile("ldmatrix.sync.aligned.m8n8.x4.trans.shared.b16 {%0,%1,%2,%3}, [%4];"
               : "=r"(r[0]), "=r"(r[1]), "=r"(r[2]), "=r"(r[3]) : "r"(a) : "memory");
}
__device__ __forceinline__ void stsm4(uint32_t a, uint32_t r0, uint32_t r1, uint32_t r2, uint32_t r3) {
  asm volatile("stmatrix.sync.aligned.m8n8.x4.shared.b16 [%0], {%1,%2,%3,%4};"
               ::"r"(a), "r"(r0), "r"(r1), "r"(r2), "r"(r3) : "memory");
}
__device__ __forceinline__ uint32_t lds32(uint32_t a) {
  uint32_t r; asm volatile("ld.shared.u32 %0, [%1];" : "=r"(r) : "r"(a) : "memory"); return r;
}
__device__ __forceinline__ uint32_t lds16(uint32_t a) {
  uint32_t r; asm volatile("{\n.reg .u16 h;\nld.shared.u16 h, [%1];\ncvt.u32.u16 %0, h;\n}\n" : "=r"(r) : "r"(a) : "memory"); return r;
}
__device__ __forceinline__ uint2 lds64(uint32_t a) {
  uint2 r; asm volatile("ld.shared.v2.u32 {%0,%1}, [%2];" : "=r"(r.x), "=r"(r.y) : "r"(a) : "memory"); return r;
}
__device__ __forceinline__ uint4 lds128(uint32_t a) {
  uint4 r;
  asm volatile("ld.shared.v4.u32 {%0,%1,%2,%3}, [%4];" : "=r"(r.x), "=r"(r.y), "=r"(r.z), "=r"(r.w) : "r"(a) : "memory");
  return r;
}
__device__ __forceinline__ void sts32(uint32_t a, uint32_t v) { asm volatile("st.shared.u32 [%0], %1;" ::"r"(a), "r"(v) : "memory"); }
__device__ __forceinline__ void sts16(uint32_t a, uint32_t v) {
  asm volatile("{\n.reg .u16 h;\ncvt.u16.u32 h, %1;\nst.shared.u16 [%0], h;\n}\n" ::"r"(a), "r"(v) : "memory");
}
__device__ __forceinline__ void sts64(uint32_t a, uint32_t x, uint32_t y) {
  asm volatile("st.shared.v2.u32 [%0], {%1,%2};" ::"r"(a), "r"(x), "r"(y) : "memory");
}
__device__ __forceinline__ void sts128(uint32_t a, uint32_t x, uint32_t y, uint32_t z, uint32_t w) {
  asm volatile("st.shared.v4.u32 [%0], {%1,%2,%3,%4};" ::"r"(a), "r"(x), "r"(y), "r"(z), "r"(w) : "memory");
}
__device__ __forceinline__ uint4 ldg_nc(const void* p) {
  uint4 r;
  asm volatile("ld.global.nc.L1::no_allocate.v4.u32 {%0,%1,%2,%3}, [%4];" : "=r"(r.x), "=r"(r.y), "=r"(r.z), "=r"(r.w) : "l"(p));
  return r;
}
__device__ __forceinline__ uint4 ld_x(const uint4* p) {
  uint4 r;
  asm volatile("ld.relaxed.gpu.global.v4.u32 {%0,%1,%2,%3}, [%4];" : "=r"(r.x), "=r"(r.y), "=r"(r.z), "=r"(r.w) : "l"(p) : "memory");
  return r;
}
__device__ __forceinline__ uint32_t ld_x32(const uint32_t* p) {
  uint32_t r; asm volatile("ld.relaxed.gpu.global.u32 %0, [%1];" : "=r"(r) : "l"(p) : "memory"); return r;
}
__device__ __forceinline__ void st_x(uint4* p, uint32_t x, uint32_t y, uint32_t z, uint32_t w) {
  asm volatile("st.relaxed.gpu.global.v4.u32 [%0], {%1,%2,%3,%4};" ::"l"(p), "r"(x), "r"(y), "r"(z), "r"(w) : "memory");
}
__device__ __forceinline__ void st_x32(uint32_t* p, uint32_t x) {
  asm volatile("st.relaxed.gpu.global.u32 [%0], %1;" ::"l"(p), "r"(x) : "memory");
}
__device__ __forceinline__ uint32_t nz(uint32_t w) { return max(w, 1u); }
__device__ __forceinline__ uint32_t min4(const uint4& v) { return min(min(v.x, v.y), min(v.z, v.w)); }

__device__ __forceinline__ void wgmma_ss_n96(float (&d)[48], uint64_t da, uint64_t db, int sc) {
  asm volatile("{\n.reg .pred p;\nsetp.ne.b32 p, %50, 0;\n"
      "wgmma.mma_async.sync.aligned.m64n96k16.f32.bf16.bf16 "
      "{%0,%1,%2,%3,%4,%5,%6,%7,%8,%9,%10,%11,%12,%13,%14,%15,%16,%17,%18,%19,%20,%21,%22,%23,%24,%25,%26,%27,%28,%29,%30,%31,%32,%33,%34,%35,%36,%37,%38,%39,%40,%41,%42,%43,%44,%45,%46,%47}, "
      "%48, %49, p, 1, 1, 0, 1;\n}\n"
      : "+f"(d[0]), "+f"(d[1]), "+f"(d[2]), "+f"(d[3]), "+f"(d[4]), "+f"(d[5]), "+f"(d[6]), "+f"(d[7]),
        "+f"(d[8]), "+f"(d[9]), "+f"(d[10]), "+f"(d[11]), "+f"(d[12]), "+f"(d[13]), "+f"(d[14]), "+f"(d[15]),
        "+f"(d[16]), "+f"(d[17]), "+f"(d[18]), "+f"(d[19]), "+f"(d[20]), "+f"(d[21]), "+f"(d[22]), "+f"(d[23]),
        "+f"(d[24]), "+f"(d[25]), "+f"(d[26]), "+f"(d[27]), "+f"(d[28]), "+f"(d[29]), "+f"(d[30]), "+f"(d[31]),
        "+f"(d[32]), "+f"(d[33]), "+f"(d[34]), "+f"(d[35]), "+f"(d[36]), "+f"(d[37]), "+f"(d[38]), "+f"(d[39]),
        "+f"(d[40]), "+f"(d[41]), "+f"(d[42]), "+f"(d[43]), "+f"(d[44]), "+f"(d[45]), "+f"(d[46]), "+f"(d[47])
      : "l"(da), "l"(db), "r"(sc));
}

__device__ __forceinline__ void wgmma_rs_n128(float (&d)[64], const uint4& a, uint64_t db, int sc) {
  asm volatile("{\n.reg .pred p;\nsetp.ne.b32 p, %69, 0;\n"
      "wgmma.mma_async.sync.aligned.m64n128k16.f32.bf16.bf16 "
      "{%0,%1,%2,%3,%4,%5,%6,%7,%8,%9,%10,%11,%12,%13,%14,%15,%16,%17,%18,%19,%20,%21,%22,%23,%24,%25,%26,%27,%28,%29,%30,%31,%32,%33,%34,%35,%36,%37,%38,%39,%40,%41,%42,%43,%44,%45,%46,%47,%48,%49,%50,%51,%52,%53,%54,%55,%56,%57,%58,%59,%60,%61,%62,%63}, "
      "{%64,%65,%66,%67}, %68, p, 1, 1, 1;\n}\n"
      : "+f"(d[0]), "+f"(d[1]), "+f"(d[2]), "+f"(d[3]), "+f"(d[4]), "+f"(d[5]), "+f"(d[6]), "+f"(d[7]),
        "+f"(d[8]), "+f"(d[9]), "+f"(d[10]), "+f"(d[11]), "+f"(d[12]), "+f"(d[13]), "+f"(d[14]), "+f"(d[15]),
        "+f"(d[16]), "+f"(d[17]), "+f"(d[18]), "+f"(d[19]), "+f"(d[20]), "+f"(d[21]), "+f"(d[22]), "+f"(d[23]),
        "+f"(d[24]), "+f"(d[25]), "+f"(d[26]), "+f"(d[27]), "+f"(d[28]), "+f"(d[29]), "+f"(d[30]), "+f"(d[31]),
        "+f"(d[32]), "+f"(d[33]), "+f"(d[34]), "+f"(d[35]), "+f"(d[36]), "+f"(d[37]), "+f"(d[38]), "+f"(d[39]),
        "+f"(d[40]), "+f"(d[41]), "+f"(d[42]), "+f"(d[43]), "+f"(d[44]), "+f"(d[45]), "+f"(d[46]), "+f"(d[47]),
        "+f"(d[48]), "+f"(d[49]), "+f"(d[50]), "+f"(d[51]), "+f"(d[52]), "+f"(d[53]), "+f"(d[54]), "+f"(d[55]),
        "+f"(d[56]), "+f"(d[57]), "+f"(d[58]), "+f"(d[59]), "+f"(d[60]), "+f"(d[61]), "+f"(d[62]), "+f"(d[63])
      : "r"(a.x), "r"(a.y), "r"(a.z), "r"(a.w), "l"(db), "r"(sc));
}

struct Params {
  const __nv_bfloat16 *x, *wphi, *wo, *u, *logA, *Aim, *Cre, *Cim, *logdt, *Dskip;
  __nv_bfloat16* out;
};

struct cpx { float r, i; };
__device__ __forceinline__ cpx cmul(cpx a, cpx b) { return {a.r * b.r - a.i * b.i, a.r * b.i + a.i * b.r}; }
__device__ __forceinline__ cpx csq(cpx a) { return {a.r * a.r - a.i * a.i, (a.r + a.r) * a.i}; }
template <bool REDUCE>
__device__ __forceinline__ cpx cexp(float a2, float f, float p) {
  float m = ex2(a2 * p);
  float t;
  if (REDUCE) {
    float k = fmaf(f, p, 12582912.f) - 12582912.f;
    t = fmaf(f, p, -k);
  } else {
    t = f * p;
  }
  t *= 6.283185307179586f;
  return {m * __cosf(t), m * __sinf(t)};
}

struct KgenRaw { uint32_t la, ai, cr, ci; float ldt; };
__device__ __forceinline__ KgenRaw kgen_load(const Params& P, int d, int half, int lane) {
  KgenRaw r;
  int o = d * 64 + half * 32 + lane;
  r.la = __ldg((const uint32_t*)P.logA + o);
  r.ai = __ldg((const uint32_t*)P.Aim + o);
  r.cr = __ldg((const uint32_t*)P.Cre + o);
  r.ci = __ldg((const uint32_t*)P.Cim + o);
  r.ldt = __bfloat162float(P.logdt[d]);
  return r;
}
__device__ __forceinline__ void kgen_operands(const KgenRaw& raw, uint32_t scr, int lane, uint32_t (&A)[8][4],
                                              uint32_t (&B)[8][5][2], float& dt, float& k2048) {
  const int g = lane >> 2, c = lane & 3;
  dt = bf_round(expf(raw.ldt));
  float ks = 0.f;
#pragma unroll
  for (int j = 0; j < 2; j++) {
    float la = j ? bf_hi(raw.la) : bf_lo(raw.la), ai = j ? bf_hi(raw.ai) : bf_lo(raw.ai);
    float cr = j ? bf_hi(raw.cr) : bf_lo(raw.cr), ci = j ? bf_hi(raw.ci) : bf_lo(raw.ci);
    float a2 = -(bf_round(expf(la)) * dt) * 1.4426950408889634f;
    float f = (ai * dt) * 0.15915494309189535f;
    f -= rintf(f);
    cpx w64 = cexp<true>(a2, f, 64.f);
    cpx we = cexp<true>(a2, f, 2048.f);
    ks += cr * we.r - ci * we.i;
    sts128(scr + (2 * lane + j) * 16, __float_as_uint(a2), __float_as_uint(f), __float_as_uint(w64.r), __float_as_uint(w64.i));
  }
  sts64(scr + 1024 + lane * 8, __byte_perm(raw.cr, raw.ci, 0x5410), __byte_perm(raw.cr, raw.ci, 0x7632));
#pragma unroll
  for (int o = 16; o; o >>= 1) ks += __shfl_xor_sync(0xffffffffu, ks, o);
  k2048 = ks;
  __syncwarp();
  const float pg = (float)g;
  const float p2 = (float)(256 + 128 * (g & 1) + (g & 6));
  const float p3 = (float)(512 + 128 * (g & 3) + (g & 4));
#pragma unroll
  for (int it = 0; it < 16; it++) {
    uint4 q = lds128(scr + (4 * it + c) * 16);
    uint32_t cw = lds32(scr + 1024 + (4 * it + c) * 4);
    float a2 = __uint_as_float(q.x), f = __uint_as_float(q.y);
    cpx w64 = {__uint_as_float(q.z), __uint_as_float(q.w)};
    cpx C = {bf_lo(cw), bf_hi(cw)};
    cpx d1 = cexp<false>(a2, f, pg);
    cpx t2 = cexp<true>(a2, f, p2);
    cpx t3 = cexp<true>(a2, f, p3);
    cpx s8 = csq(csq(csq(d1)));
    cpx z = cmul(s8, w64);
    cpx a0 = cmul(C, s8), a1 = cmul(C, z);
    cpx t1 = cmul(d1, csq(w64));
    cpx t4 = csq(csq(csq(csq(z))));
    const int ksx = it >> 1, h = it & 1;
    A[ksx][2 * h] = pack_bf(a0.r, -a0.i);
    A[ksx][2 * h + 1] = pack_bf(a1.r, -a1.i);
    B[ksx][0][h] = pack_bf(d1.r, d1.i);
    B[ksx][1][h] = pack_bf(t1.r, t1.i);
    B[ksx][2][h] = pack_bf(t2.r, t2.i);
    B[ksx][3][h] = pack_bf(t3.r, t3.i);
    B[ksx][4][h] = pack_bf(t4.r, t4.i);
  }
}
__device__ __forceinline__ void kgen_mma(const uint32_t (&A)[8][4], const uint32_t (&B)[8][5][2], float (&k)[5][4]) {
#pragma unroll
  for (int j = 0; j < 5; j++) mma0(k[j][0], k[j][1], k[j][2], k[j][3], A[0][0], A[0][1], A[0][2], A[0][3], B[0][j][0], B[0][j][1]);
#pragma unroll
  for (int s = 1; s < 8; s++)
#pragma unroll
    for (int j = 0; j < 5; j++) mma(k[j][0], k[j][1], k[j][2], k[j][3], A[s][0], A[s][1], A[s][2], A[s][3], B[s][j][0], B[s][j][1]);
}

__device__ __forceinline__ void build_tables(uint32_t tb, int lane, float (&k)[5][4], float k2048) {
  const int g = lane >> 2, c = lane & 3;
  const uint32_t kc = tb + T_KC + 16;
#pragma unroll
  for (int r = 0; r < 2; r++) {
    const int row = g + 8 * r;
    sts32(kc + 2 * (8 * row + 2 * c), pack_bf(k[0][2 * r], k[0][2 * r + 1]));
    sts32(kc + 2 * (128 + 8 * row + 2 * c), pack_bf(k[1][2 * r], k[1][2 * r + 1]));
    uint32_t w2 = pack_bf(k[2][2 * r], k[2][2 * r + 1]);
    uint32_t w3 = pack_bf(k[3][2 * r], k[3][2 * r + 1]);
    uint32_t w4 = pack_bf(k[4][2 * r], k[4][2 * r + 1]);
    const int i2 = 256 + 4 * row + c;
    const int i3 = 384 + 2 * row + 64 * (c & 1) + (c >> 1);
    const int i4 = 512 + row + 32 * c;
    sts16(kc + 2 * i2, w2); sts16(kc + 2 * (i2 + 64), w2 >> 16);
    sts16(kc + 2 * i3, w3); sts16(kc + 2 * (i3 + 32), w3 >> 16);
    sts16(kc + 2 * i4, w4); sts16(kc + 2 * (i4 + 16), w4 >> 16);
  }
  if (lane == 0) { sts16(kc + 2 * 640, pack_bf(k2048, 0.f)); sts16(kc - 2, 0); }
  __syncwarp();
  const uint32_t td = tb + T_D + 32;
  {
    uint4 v = lds128(kc + 16 * lane);
    uint32_t pv = lds16(kc + 16 * lane - 2);
    sts128(td + 32 * lane, __byte_perm(v.x, pv, 0x5410), __byte_perm(v.x, v.x, 0x1032), __byte_perm(v.y, v.x, 0x7610),
           __byte_perm(v.y, v.y, 0x1032));
    sts128(td + 32 * lane + 16, __byte_perm(v.z, v.y, 0x7610), __byte_perm(v.z, v.z, 0x1032),
           __byte_perm(v.w, v.z, 0x7610), __byte_perm(v.w, v.w, 0x1032));
  }
  {
    uint2 v = lds64(kc + 512 + 8 * lane);
    uint32_t k4 = lds16(kc + 512 + 8 * lane + 8);
    uint32_t pv = lds16(kc + (lane == 0 ? 510 : 512 + 8 * lane));
    sts128(td + 1024 + 32 * lane, __byte_perm(v.x, pv, 0x5410), __byte_perm(v.x, v.x, 0x1010),
           __byte_perm(v.x, v.x, 0x1032), __byte_perm(v.y, v.x, 0x7610));
    sts128(td + 1024 + 32 * lane + 16, __byte_perm(v.y, v.y, 0x1010), __byte_perm(v.y, v.y, 0x1010),
           __byte_perm(v.y, v.y, 0x1032), __byte_perm(k4, v.y, 0x7610));
  }
  {
    uint32_t kk = lds16(kc + 2 * 384);
    uint32_t w = lane < 3 ? (kk | (kk << 16)) : (lane == 3 ? (kk << 16) : 0u);
    if (lane < 24) sts32(td + 4 * (lane < 16 ? 512 + lane : lane - 24), w);
  }
#pragma unroll
  for (int s = 0; s < 2; s++) {
    const uint32_t b = kc + 2 * (s ? 512 : 384) + 8 * lane;
    uint2 v = lds64(b);
    uint32_t em = lds16(b - 2), e4 = lds16(b + 8);
    uint32_t e0 = v.x;
    if (lane == 0) { em = 0; e0 = 0; }
    const uint32_t to = tb + (s ? T_7 : T_3) + 64, te = tb + (s ? T_9 : T_5) + 64;
    sts64(to + 8 * lane, __byte_perm(v.x, em, 0x5432), __byte_perm(v.y, v.x, 0x7632));
    sts64(te + 8 * lane, __byte_perm(v.y, e0, 0x5410), __byte_perm(e4, v.y, 0x5410));
    if (s == 0) {
      uint32_t lo_ = lds16(kc + 2 * 511), le_ = lds16(kc + 2 * 512);
      const int j = lane < 16 ? lane - 16 : 48 + lane;
      sts32(to + 4 * j, lane == 16 ? (lo_ << 16) : 0u);
      sts32(te + 4 * j, lane == 16 ? (le_ << 16) : 0u);
    } else {
      sts32((lane < 16 ? to : te) + 4 * ((lane & 15) - 16), 0u);
    }
  }
  __syncwarp();
}

__device__ __forceinline__ uint32_t box2w(int lo, int hi, int o0, int o1) {
  return ((o0 >= lo && o0 <= hi) ? 0x3F80u : 0u) | ((o1 >= lo && o1 <= hi) ? 0x3F800000u : 0u);
}

__device__ __forceinline__ void conv_channel(uint32_t ub, uint32_t tb, int lane, uint4* ydst) {
  const int g = lane >> 2, c = lane & 3;
  float acc[16][4];
  const uint32_t hb = ub + U_PAD + ((lane >> 3) & 1) * U_ODD + 16 * ((lane >> 4) + (lane & 7));
  {
    const int oh = c < 2 ? 8 + 2 * c : 2 * c - 8;
    const uint32_t bx0 = box2w(g - 4, g + 4, 2 * c, 2 * c + 1), bx1 = box2w(g - 3, g + 3, 2 * c, 2 * c + 1);
    const uint32_t bx2 = box2w(g - 4, g + 4, oh, oh + 1), bx3 = box2w(g - 3, g + 3, oh, oh + 1);
    const uint32_t kv = lds16(tb + T_KC + 16 + 2 * 512);
    const int x = g - 2 * c;
    const uint32_t lb0 = (x == -5 || x == -4 ? kv : 0u) | (x == -4 || x == -3 ? kv << 16 : 0u);
    const uint32_t lb1 = (x == 3 || x == 4 ? kv : 0u) | (x == 4 || x == 5 ? kv << 16 : 0u);
    uint32_t z09[8], z07[8], zm9[8], zm7[8];
#pragma unroll
    for (int i = 0; i < 8; i++) {
      uint32_t h[4];
      ldsm4(h, hb + 8 * (16 * i - 2));
      float y0, y1, y2, y3, w0, w1, w2, w3;
      mma0(y0, y1, y2, y3, bx0, bx1, bx2, bx3, h[2], c < 2 ? h[3] : h[1]);
      mma0(w0, w1, w2, w3, bx0, bx1, bx2, bx3, h[1], c < 2 ? h[2] : h[0]);
      mma0(acc[8 + i][0], acc[8 + i][1], acc[8 + i][2], acc[8 + i][3], h[1], h[2], h[2], h[3], lb0, lb1);
      z09[i] = pack_bf(y0, y1); z07[i] = pack_bf(y2, y3);
      zm9[i] = pack_bf(w0, w1); zm7[i] = pack_bf(w2, w3);
    }
    uint32_t f7[9], f9a[9], f9b[9];
#pragma unroll
    for (int m = 0; m < 9; m++) {
      f7[m] = lds32(tb + T_7 + 4 * (8 * (m + 7) - 48 + x));
      f9b[m] = lds32(tb + T_9 + 4 * (8 * (m + 7) - 48 + x));
      f9a[m] = lds32(tb + T_9 + 4 * (8 * (m + 7) - 49 + x));
    }
#pragma unroll
    for (int kap = 0; kap < 4; kap++)
#pragma unroll
      for (int sg = 0; sg < 2; sg++)
#pragma unroll
        for (int bk = 4 + kap; bk < 8; bk++) {
          const int m = 2 * (bk - kap) - 7;
          if (sg == 0) {
            mma(acc[2 * bk][0], acc[2 * bk][1], acc[2 * bk + 1][0], acc[2 * bk + 1][1], f9a[m], f9a[m + 1], f9a[m - 1], f9a[m], z09[2 * kap], z09[2 * kap + 1]);
            mma(acc[2 * bk][2], acc[2 * bk][3], acc[2 * bk + 1][2], acc[2 * bk + 1][3], f9b[m], f9b[m + 1], f9b[m - 1], f9b[m], zm9[2 * kap], zm9[2 * kap + 1]);
          } else {
            mma(acc[2 * bk][0], acc[2 * bk][1], acc[2 * bk + 1][0], acc[2 * bk + 1][1], f7[m], f7[m + 1], f7[m - 1], f7[m], zm7[2 * kap], zm7[2 * kap + 1]);
            mma(acc[2 * bk][2], acc[2 * bk][3], acc[2 * bk + 1][2], acc[2 * bk + 1][3], f7[m], f7[m + 1], f7[m - 1], f7[m], z07[2 * kap], z07[2 * kap + 1]);
          }
        }
  }
  {
#pragma unroll
    for (int b = 0; b < 8; b++) acc[b][0] = acc[b][1] = acc[b][2] = acc[b][3] = 0.f;
    const int oh = c < 3 ? 2 * c : -10;
    const uint32_t bx0 = box2w(g - 10, g - 6, 2 * c - 8, 2 * c - 7), bx1 = box2w(g - 5, g - 3, 2 * c - 8, 2 * c - 7);
    const uint32_t bx2 = box2w(g - 10, g - 6, oh, oh + 1), bx3 = box2w(g - 5, g - 3, oh, oh + 1);
    const int q0 = g - 1, q1 = c < 3 ? g : g - 2;
    const uint32_t y0a = ub + U_PAD + (q0 & 1) * U_ODD + 16 * (q0 >> 1) + 4 * c;
    const uint32_t y1a = ub + U_PAD + (q1 & 1) * U_ODD + 16 * (q1 >> 1) + 4 * c;
    uint2 a5[10], a3[10];
#pragma unroll
    for (int m = 0; m < 10; m++) {
      a5[m] = lds64(tb + T_5 + 4 * (8 * (m + 7) - 48 + 2 * g - 2 * c));
      a3[m] = lds64(tb + T_3 + 4 * (8 * (m + 7) - 48 + 2 * g - 2 * c));
    }
    uint32_t x5[3][2], x3[3][2];
    auto ygen = [&](int kap) {
#pragma unroll
      for (int hh = 0; hh < 2; hh++) {
        uint32_t b0 = lds32(y0a + 64 * (2 * kap + hh)), b1 = lds32(y1a + 64 * (2 * kap + hh));
        float y0, y1, y2, y3;
        mma0(y0, y1, y2, y3, bx0, bx1, bx2, bx3, b0, b1);
        x5[kap % 3][hh] = pack_bf(y0, y1);
        x3[kap % 3][hh] = pack_bf(y2, y3);
      }
    };
    ygen(0);
    ygen(1);
#pragma unroll
    for (int kap = 0; kap < 12; kap++) {
      if (kap + 2 < 12) ygen(kap + 2);
#pragma unroll
      for (int sg = 0; sg < 2; sg++)
#pragma unroll
        for (int D = 4; D <= 8; D++) {
          const int be = kap + D, m = 2 * D - 7;
          if (be <= 15) {
            if (sg == 0) mma(acc[be][0], acc[be][1], acc[be][2], acc[be][3], a5[m].x, a5[m].y, a5[m - 1].x, a5[m - 1].y, x5[kap % 3][0], x5[kap % 3][1]);
            else mma(acc[be][0], acc[be][1], acc[be][2], acc[be][3], a3[m].x, a3[m].y, a3[m - 1].x, a3[m - 1].y, x3[kap % 3][0], x3[kap % 3][1]);
          }
        }
    }
  }
  {
    uint32_t F[66];
    const uint32_t fa = tb + T_D + 32 + 4 * (g - 2 * c);
#pragma unroll
    for (int m = 0; m < 66; m++) F[m] = lds32(fa + 32 * m);
    uint32_t H[3][4];
    ldsm4(H[0], hb + 8 * 238);
    ldsm4(H[1], hb + 8 * 234);
#pragma unroll
    for (int q = 0; q < 64; q++) {
      if (q + 2 < 64) ldsm4(H[(q + 2) % 3], hb + 8 * (238 - 4 * (q + 2)));
      const uint32_t(&h)[4] = H[q % 3];
      const uint32_t hn = (q + 1 < 64) ? H[(q + 1) % 3][3] : 0u;
#pragma unroll
      for (int hh = 0; hh < 2; hh++) {
        const int s = 120 - 2 * q - hh;
        const uint32_t a0 = hh ? hn : h[1], a1 = hh ? h[0] : h[2], a3 = hh ? h[1] : h[3];
#pragma unroll
        for (int be = 15; be >= 0; be--) {
          const int de = 8 * be - s;
          if (de >= 0 && de <= 32) mma(acc[be][0], acc[be][1], acc[be][2], acc[be][3], a0, a1, a1, a3, F[2 * de + 1], F[2 * de]);
        }
#pragma unroll
        for (int B = 7; B >= 0; B--) {
          const int last = (16 * B - 32 > -7) ? 16 * B - 32 : -7;
          const int when = (last - 3 > -7) ? last - 3 : -7;
          if (s == when)
            st_x(ydst + B * 32, nz(pack_bf(acc[2 * B][0], acc[2 * B][1])), nz(pack_bf(acc[2 * B][2], acc[2 * B][3])),
                 nz(pack_bf(acc[2 * B + 1][0], acc[2 * B + 1][1])), nz(pack_bf(acc[2 * B + 1][2], acc[2 * B + 1][3])));
        }
      }
    }
  }
}

__device__ __forceinline__ void dual_exp(const float (&p)[8], float (&ep)[8], float (&em)[8]) {
  const float L = 1.4426950408889634f;
  uint32_t w[4] = {pack_bf(p[0], p[2]), pack_bf(p[1], p[3]), pack_bf(p[4], p[6]), pack_bf(p[5], p[7])};
  uint32_t mx = bmax2(bmax2(w[0], w[1]), bmax2(w[2], w[3]));
  uint32_t mn = bmin2(bmin2(w[0], w[1]), bmin2(w[2], w[3]));
  mx = bmax2(mx, __shfl_xor_sync(0xffffffffu, mx, 1));
  mn = bmin2(mn, __shfl_xor_sync(0xffffffffu, mn, 1));
  mx = bmax2(mx, __shfl_xor_sync(0xffffffffu, mx, 2));
  mn = bmin2(mn, __shfl_xor_sync(0xffffffffu, mn, 2));
  const float mx0 = __fmul_rn(bf_lo(mx), L), mx1 = __fmul_rn(bf_hi(mx), L);
  const float mn0 = __fmul_rn(bf_lo(mn), L), mn1 = __fmul_rn(bf_hi(mn), L);
#pragma unroll
  for (int i = 0; i < 4; i++) {
    const int b = (i >> 1) * 4 + (i & 1);
    const float x0 = __fmul_rn(bf_lo(w[i]), L), x1 = __fmul_rn(bf_hi(w[i]), L);
    ep[b] = ex2(__fsub_rn(x0, mx0)); em[b] = ex2(__fsub_rn(mn0, x0));
    ep[b + 2] = ex2(__fsub_rn(x1, mx1)); em[b + 2] = ex2(__fsub_rn(mn1, x1));
  }
}
__device__ __forceinline__ void feat(const float (&acc)[48], int j0, const uint32_t (&wf)[4], float (&p)[8]) {
  const uint32_t a0 = pack_bf(acc[4 * j0], acc[4 * j0 + 1]), a1 = pack_bf(acc[4 * j0 + 2], acc[4 * j0 + 3]);
  const uint32_t a2 = pack_bf(acc[4 * j0 + 4], acc[4 * j0 + 5]), a3 = pack_bf(acc[4 * j0 + 6], acc[4 * j0 + 7]);
  mma0(p[0], p[1], p[2], p[3], a0, a1, a2, a3, wf[0], wf[1]);
  mma0(p[4], p[5], p[6], p[7], a0, a1, a2, a3, wf[2], wf[3]);
}
__device__ __forceinline__ void phik_store(const float (&p)[8], uint32_t dst) {
  float ep[8], em[8];
  dual_exp(p, ep, em);
  float s[4] = {(ep[0] + ep[1]) + (ep[4] + ep[5]), (ep[2] + ep[3]) + (ep[6] + ep[7]),
                (em[0] + em[1]) + (em[4] + em[5]), (em[2] + em[3]) + (em[6] + em[7])};
#pragma unroll
  for (int i = 0; i < 4; i++) s[i] += __shfl_xor_sync(0xffffffffu, s[i], 1);
#pragma unroll
  for (int i = 0; i < 4; i++) s[i] += __shfl_xor_sync(0xffffffffu, s[i], 2);
#pragma unroll
  for (int i = 0; i < 4; i++) s[i] = rcp(s[i]);
  stsm4(dst, pack_bf(ep[0] * s[0], ep[1] * s[0]), pack_bf(ep[2] * s[1], ep[3] * s[1]),
        pack_bf(ep[4] * s[0], ep[5] * s[0]), pack_bf(ep[6] * s[1], ep[7] * s[1]));
  stsm4(dst + 512, pack_bf(em[0] * s[2], em[1] * s[2]), pack_bf(em[2] * s[3], em[3] * s[3]),
        pack_bf(em[4] * s[2], em[5] * s[2]), pack_bf(em[6] * s[3], em[7] * s[3]));
}
__device__ __forceinline__ void v_store(const float (&acc)[48], int j0, uint32_t dst) {
  stsm4(dst, pack_bf(acc[4 * j0], acc[4 * j0 + 1]), pack_bf(acc[4 * j0 + 2], acc[4 * j0 + 3]),
        pack_bf(acc[4 * j0 + 4], acc[4 * j0 + 5]), pack_bf(acc[4 * j0 + 6], acc[4 * j0 + 7]));
}
__device__ __forceinline__ void phiq_pack(const float (&p)[8], uint32_t (&e)[8]) {
  float ep[8], em[8];
  dual_exp(p, ep, em);
#pragma unroll
  for (int i = 0; i < 4; i++) { e[i] = pack_bf(ep[2 * i], ep[2 * i + 1]); e[4 + i] = pack_bf(em[2 * i], em[2 * i + 1]); }
}
template <int NS>
__device__ __forceinline__ void contract(uint32_t stg, int w, int lane, float (&kv)[12]) {
  uint32_t a[NS][4], b[NS][4];
#pragma unroll
  for (int s = 0; s < NS; s++) {
    ldsm4t(a[s], stg + s * 3072 + w * 512 + lane * 16);
    ldsm4t(b[s], stg + s * 3072 + 2048 + (w >> 1) * 512 + lane * 16);
  }
#pragma unroll
  for (int s = 0; s < NS; s++) {
    mma(kv[0], kv[1], kv[2], kv[3], a[s][0], a[s][2], a[s][1], a[s][3], b[s][0], b[s][1]);
    mma(kv[4], kv[5], kv[6], kv[7], a[s][0], a[s][2], a[s][1], a[s][3], b[s][2], b[s][3]);
    mma(kv[8], kv[9], kv[10], kv[11], a[s][0], a[s][2], a[s][1], a[s][3], 0x3F803F80u, 0x3F803F80u);
  }
}
__device__ __forceinline__ uint32_t wo_addr(int kb) { return kb < 6 ? OFF_W + kb * 16384 : OFF_X + (kb - 6) * 16384; }

__global__ void __launch_bounds__(NTHREADS, 1)
fused_kernel(const __grid_constant__ CUtensorMap mx, const __grid_constant__ CUtensorMap mw,
             const __grid_constant__ CUtensorMap mo, const Params P) {
  extern __shared__ uint8_t smem_raw[];
  const uint32_t sb = (smem_u32(smem_raw) + 1023u) & ~1023u;
  const uint32_t bars = sb + OFF_BAR;
  const int tid = threadIdx.x, lane = tid & 31;
  const int warp = __shfl_sync(0xffffffffu, tid >> 5, 0);
  const int b = blockIdx.x, oct = b >> 3, i8 = b & 7;
  const int rt = oct < 8 ? oct : 15 - oct;
  const int hp = (oct >> 3) * 8 + i8;

  if (tid == 384) {
    asm volatile("prefetch.tensormap [%0];" ::"l"(&mw) : "memory");
    asm volatile("prefetch.tensormap [%0];" ::"l"(&mx) : "memory");
    for (int i = 0; i < 12; i++) mbar_init(bars + 8 * i, 1);
    for (int i = 0; i < 4; i++) mbar_init(bars + 8 * (MB_XEMPTY + i), 4);
    for (int i = 0; i < 9; i++) mbar_init(bars + 8 * (MB_WOFULL + i), 1);
    mbar_init(bars + 8 * MB_GDONE, 4);
    asm volatile("fence.mbarrier_init.release.cluster;" ::: "memory");
#pragma unroll
    for (int kb = 0; kb < 8; kb++) {
      mbar_expect(bars + 8 * (MB_WFULL + kb), 12288);
      tma3d(sb + OFF_W + kb * 12288, &mw, bars + 8 * (MB_WFULL + kb), hp * 32, kb * 64, 0);
      if (kb < 4) {
        mbar_expect(bars + 8 * (MB_XFULL + kb), 16384);
        tma2d(sb + OFF_X + kb * 16384, &mx, bars + 8 * (MB_XFULL + kb), kb * 64, rt * 256);
      }
    }
  }
  __syncthreads();

  if (warp >= 12) {
    asm volatile("setmaxnreg.dec.sync.aligned.u32 32;");
    if (warp == 12) {
      if (lane == 0) {
        l2_prefetch(P.x + (size_t)(rt * 256 + hp * 16) * 512, 16384);
        l2_prefetch(P.wo + (size_t)b * 2048, 4096);
        asm volatile("prefetch.tensormap [%0];" ::"l"(&mo) : "memory");
        const int cq = hp & 3;
#pragma unroll 1
        for (int n = 0; n < 16; n++) {
          mbar_wait(bars + 8 * (MB_XEMPTY + (n & 3)), (n >> 2) & 1);
          if (n < 12) {
            const int m = n + 4;
            mbar_expect(bars + 8 * (MB_XFULL + (n & 3)), 16384);
            tma2d(sb + OFF_X + (n & 3) * 16384, &mx, bars + 8 * (MB_XFULL + (n & 3)), (m & 7) * 64, rt * 256 + (m >> 3) * 128);
          }
          int w0 = -1, w1 = -1;
          if (n >= 9 && n <= 11) w0 = n - 9;
          else if (n == 12) w0 = 6;
          else if (n == 13) { w0 = 3; w1 = 7; }
          else if (n >= 14) w0 = n - 10;
          if (w0 >= 0) {
            mbar_expect(bars + 8 * (MB_WOFULL + w0), 16384);
            tma3d(sb + wo_addr(w0), &mo, bars + 8 * (MB_WOFULL + w0), 0, w0 * 64, cq * 2);
          }
          if (w1 >= 0) {
            mbar_expect(bars + 8 * (MB_WOFULL + w1), 16384);
            tma3d(sb + wo_addr(w1), &mo, bars + 8 * (MB_WOFULL + w1), 0, w1 * 64, cq * 2);
          }
        }
      }
    } else {
      unsigned target = 0;
      if (tid == 416) target = (ld_x32(&g_cnt) & ~(unsigned)(NCTA - 1)) + NCTA;
      const int t = tid - 416;
      uint4* po = g_o + (size_t)(rt * 4 * 32 + hp * 2) * 128;
      uint4* py = g_y + (size_t)b * 1024;
      uint4* pp = g_part + (size_t)(hp * 8 + rt) * 256;
#pragma unroll 1
      for (int i = t; i < 1024; i += 96) {
        st_x(po + (i >> 8) * 4096 + (i & 255), 0, 0, 0, 0);
        st_x(py + i, 0, 0, 0, 0);
        if (i < 256) st_x(pp + i, 0, 0, 0, 0);
      }
      if (t < 16) st_x(g_z + (hp * 8 + rt) * 16 + t, 0, 0, 0, 0);
      if (warp > 13) {
        nb_arrive(NB_INIT, 224);
      } else {
        nb_sync(NB_INIT, 224);
        if (lane == 0) {
          asm volatile("fence.proxy.async.global;" ::: "memory");
          asm volatile("red.release.gpu.global.add.u32 [%0], 1;" ::"l"(&g_cnt) : "memory");
          for (int i = 0; i < SPIN_MAX; i++) {
            unsigned v;
            asm volatile("ld.acquire.gpu.global.u32 %0, [%1];" : "=r"(v) : "l"(&g_cnt) : "memory");
            if ((int)(v - target) >= 0) break;
            __nanosleep(100);
          }
          asm volatile("fence.proxy.async.global;" ::: "memory");
          mbar_expect(bars + 8 * MB_UFULL, 16384);
#pragma unroll 1
          for (int i = 0; i < 8; i++)
            bulk_g2s(sb + OFF_U + (i >> 1) * U_CH + (i & 1) * U_ODD + U_PAD, g_uT + (size_t)(b * 8 + i) * 128, 2048,
                     bars + 8 * MB_UFULL);
        }
      }
    }
  } else if (warp >= 8) {
    asm volatile("setmaxnreg.inc.sync.aligned.u32 160;");
    const int w = warp - 8, d = b * 4 + w;
    const uint32_t ub = sb + OFF_U + w * U_CH, tb = sb + OFF_T + w * T_CH;
    KgenRaw raw = kgen_load(P, d, 0, lane);
    const float dsk = __bfloat162float(P.Dskip[d]);
    if (lane < 16) sts128(ub + (lane >> 3) * U_ODD + (lane & 7) * 16, 0, 0, 0, 0);
    TS(32);
    float k[5][4], dt, k2048;
    {
      uint32_t A[8][4], B[8][5][2];
      kgen_operands(raw, sb + OFF_STG0 + w * 1536, lane, A, B, dt, k2048);
      TS(33);
      nb_sync(NB_OPEN, 384);
      kgen_mma(A, B, k);
      nb_arrive(NB_CLOSE, 384);
    }
    TS(34);
    nb_sync(NB_KPART, 256);
    {
      const float sc = 2.f * dt;
#pragma unroll
      for (int j = 0; j < 5; j++) {
        uint4 v = lds128(tb + j * 512 + lane * 16);
        k[j][0] = (k[j][0] + __uint_as_float(v.x)) * sc; k[j][1] = (k[j][1] + __uint_as_float(v.y)) * sc;
        k[j][2] = (k[j][2] + __uint_as_float(v.z)) * sc; k[j][3] = (k[j][3] + __uint_as_float(v.w)) * sc;
      }
      k2048 = (k2048 + __uint_as_float(lds32(tb + 2560))) * sc;
      if (lane == 0) k[0][0] += dsk;
      __syncwarp();
    }
    build_tables(tb, lane, k, k2048);
    TS(35);
    mbar_wait(bars + 8 * MB_UFULL, 0);
    mbar_wait(bars + 8 * MB_GDONE, 0);
    TS(36);
    conv_channel(ub, tb, lane, g_y + (size_t)d * 256 + lane);
    nb_arrive(NB_BDONE, 384);
    TS(37);
    {
      const int lam = w * 8 + (lane >> 2), o = lane & 3;
      const uint4* src = g_y + (size_t)(oct * 32 + o * 8) * 256 + i8 * 32 + lam;
      uint4 v[8];
      for (int it = 0; it < SPIN_MAX; it++) {
        uint32_t m = 0xffffffffu;
#pragma unroll
        for (int i = 0; i < 8; i++) v[i] = ld_x(src + i * 256);
#pragma unroll
        for (int i = 0; i < 8; i++) m = min(m, min4(v[i]));
        if (__all_sync(0xffffffffu, m != 0)) break;
      }
      __nv_bfloat16* dst = P.out + (size_t)(i8 * 256 + (lam >> 2) * 16 + (lam & 3) * 2) * 1024 + 512 + oct * 32 + o * 8;
#pragma unroll
      for (int kk = 0; kk < 4; kk++)
#pragma unroll
        for (int f = 0; f < 2; f++) {
          uint32_t r[4];
#pragma unroll
          for (int m = 0; m < 4; m++) {
            const uint4 &ra = v[2 * m], &rb = v[2 * m + 1];
            const uint32_t xa = kk == 0 ? ra.x : kk == 1 ? ra.y : kk == 2 ? ra.z : ra.w;
            const uint32_t xb = kk == 0 ? rb.x : kk == 1 ? rb.y : kk == 2 ? rb.z : rb.w;
            r[m] = __byte_perm(xa, xb, f ? 0x7632 : 0x5410);
          }
          *(uint4*)(dst + (size_t)((kk >> 1) * 128 + (kk & 1) * 8 + f) * 1024) = make_uint4(r[0], r[1], r[2], r[3]);
        }
    }
    TS(38);
  } else {
    asm volatile("setmaxnreg.inc.sync.aligned.u32 160;");
    const int wg = warp >> 2, w = warp & 3, t = tid & 127;
    const int g = lane >> 2, c = lane & 3;
    uint32_t wf[2][4];
    {
      const unsigned short* wp = (const unsigned short*)P.wphi + hp * 512;
#pragma unroll
      for (int h = 0; h < 2; h++)
#pragma unroll
        for (int i = 0; i < 4; i++) {
          const int o = h * 256 + (2 * c + (i & 1) * 8) * 16 + g + (i >> 1) * 8;
          wf[h][i] = (uint32_t)__ldg(wp + o) | ((uint32_t)__ldg(wp + o + 16) << 16);
        }
    }
    if (wg == 0) {
      const int r0 = oct * 128 + w * 32 + (lane >> 3) * 8, c0 = i8 * 64 + (lane & 7) * 8;
      uint4 row[8];
#pragma unroll
      for (int i = 0; i < 8; i++) row[i] = ldg_nc(P.u + (size_t)(r0 + i) * 512 + c0);
      const int q = r0 >> 3;
      uint4* dst = g_uT + (size_t)c0 * 256 + (q & 1) * 128 + (q >> 1);
#pragma unroll
      for (int i = 0; i < 8; i++) {
        const uint32_t sel = (i & 1) ? 0x7632 : 0x5410;
        uint32_t o[4];
#pragma unroll
        for (int m = 0; m < 4; m++) {
          const uint4 &ra = row[2 * m], &rb = row[2 * m + 1];
          const uint32_t xa = (i >> 1) == 0 ? ra.x : (i >> 1) == 1 ? ra.y : (i >> 1) == 2 ? ra.z : ra.w;
          const uint32_t xb = (i >> 1) == 0 ? rb.x : (i >> 1) == 1 ? rb.y : (i >> 1) == 2 ? rb.z : rb.w;
          o[m] = __byte_perm(xa, xb, sel);
        }
        dst[i * 256] = make_uint4(o[0], o[1], o[2], o[3]);
      }
      asm volatile("fence.proxy.async.global;" ::: "memory");
      nb_arrive(NB_INIT, 224);
      TS(1);
    } else {
      KgenRaw raw = kgen_load(P, b * 4 + w, 1, lane);
      float k[5][4], dt, k2048;
      uint32_t A[8][4], B[8][5][2];
      kgen_operands(raw, sb + OFF_STG0 + (4 + w) * 1536, lane, A, B, dt, k2048);
      TS(16);
      nb_sync(NB_OPEN, 384);
      kgen_mma(A, B, k);
      const uint32_t tb = sb + OFF_T + w * T_CH;
#pragma unroll
      for (int j = 0; j < 5; j++)
        sts128(tb + j * 512 + lane * 16, __float_as_uint(k[j][0]), __float_as_uint(k[j][1]), __float_as_uint(k[j][2]),
               __float_as_uint(k[j][3]));
      if (lane == 0) sts32(tb + 2560, __float_as_uint(k2048));
      nb_arrive(NB_KPART, 256);
      nb_sync(NB_CLOSE, 384);
      TS(17);
    }
    float acc[2][48];
#pragma unroll 1
    for (int kb = 0; kb < 8; kb++) {
      const int n = wg * 8 + kb;
      mbar_wait(bars + 8 * (MB_WFULL + kb), 0);
      mbar_wait(bars + 8 * (MB_XFULL + (n & 3)), (n >> 2) & 1);
      if (kb == 0) TS(wg * 16 + 2);
      const uint64_t da = mkdesc(sb + OFF_X + (n & 3) * 16384, 16, 1024, 1);
      const uint64_t db = mkdesc(sb + OFF_W + kb * 12288, 4096, 512, 2);
      WG_FENCE();
#pragma unroll
      for (int k = 0; k < 4; k++) {
        wgmma_ss_n96(acc[0], da + 2 * k, db + 64 * k, kb | k);
        wgmma_ss_n96(acc[1], da + 2 * k + 512, db + 64 * k, kb | k);
      }
      WG_COMMIT();
      if (kb > 0) {
        WG_WAIT(1);
        if (lane == 0) mbar_arrive(bars + 8 * (MB_XEMPTY + ((n - 1) & 3)));
      }
    }
    WG_WAIT(0);
    if (lane == 0) {
      if (wg) mbar_arrive(bars + 8 * MB_GDONE);
      mbar_arrive(bars + 8 * (MB_XEMPTY + 3));
    }
    TS(wg * 16 + 3);

    uint32_t eq[2][2][8];
    const uint32_t kvs = sb + OFF_STG0;
    if (wg == 0) {
      nb_arrive(NB_OPEN, 384);
      float pk[2][2][8], pq[2][2][8];
#pragma unroll
      for (int mt = 0; mt < 2; mt++)
#pragma unroll
        for (int h = 0; h < 2; h++) { feat(acc[mt], 4 + 2 * h, wf[h], pk[mt][h]); feat(acc[mt], 2 * h, wf[h], pq[mt][h]); }
      nb_sync(NB_CLOSE, 384);
      const uint32_t stg = sb + OFF_STG0;
#pragma unroll
      for (int mt = 0; mt < 2; mt++) {
        const uint32_t sl = stg + (mt * 4 + w) * 3072 + lane * 16;
#pragma unroll
        for (int h = 0; h < 2; h++) { v_store(acc[mt], 8 + 2 * h, sl + 2048 + h * 512); phik_store(pk[mt][h], sl + h * 1024); }
      }
#pragma unroll
      for (int mt = 0; mt < 2; mt++)
#pragma unroll
        for (int h = 0; h < 2; h++) phiq_pack(pq[mt][h], eq[mt][h]);
      TS(4);
      nb_sync(NB_WG0, 128);
      mbar_wait(bars + 8 * MB_UFULL, 0);
      mbar_wait(bars + 8 * MB_GDONE, 0);
      float kv[12];
#pragma unroll
      for (int i = 0; i < 12; i++) kv[i] = 0.f;
      contract<4>(stg, w, lane, kv);
      contract<4>(stg + 12288, w, lane, kv);
      const uint32_t stg1 = sb + OFF_X + 32768;
      nb_sync(NB_ST0, 256);
      contract<4>(stg1, w, lane, kv);
      nb_sync(NB_ST1, 256);
      contract<4>(stg1 + 12288, w, lane, kv);
      uint4* pp = g_part + (size_t)(hp * 8 + rt) * 256 + t;
      st_x(pp, nz(__float_as_uint(kv[0])), nz(__float_as_uint(kv[1])), nz(__float_as_uint(kv[2])), nz(__float_as_uint(kv[3])));
      st_x(pp + 128, nz(__float_as_uint(kv[4])), nz(__float_as_uint(kv[5])), nz(__float_as_uint(kv[6])), nz(__float_as_uint(kv[7])));
      if (c == 0) {
        uint32_t* pz = (uint32_t*)(g_z + (hp * 8 + rt) * 16) + w * 16 + g;
        st_x32(pz, nz(__float_as_uint(kv[8])));
        st_x32(pz + 8, nz(__float_as_uint(kv[10])));
      }
      TS(5);
      const uint4* ps = g_part + (size_t)hp * 8 * 256 + t;
      const uint32_t* zs = (const uint32_t*)(g_z + hp * 8 * 16) + (lane >> 4) * 256 + w * 16 + (lane & 15);
      uint4 v[16];
      uint32_t zv[4];
      for (int it = 0; it < SPIN_MAX; it++) {
#pragma unroll
        for (int i = 0; i < 16; i++) v[i] = ld_x(ps + i * 128);
#pragma unroll
        for (int i = 0; i < 4; i++) zv[i] = ld_x32(zs + i * 64);
        uint32_t m = min(min(zv[0], zv[1]), min(zv[2], zv[3]));
#pragma unroll
        for (int i = 0; i < 16; i++) m = min(m, min4(v[i]));
        if (__all_sync(0xffffffffu, m != 0)) break;
      }
      float s[8];
#pragma unroll
      for (int i = 0; i < 8; i++) s[i] = 0.f;
#pragma unroll
      for (int r = 0; r < 8; r++) {
        s[0] += __uint_as_float(v[2 * r].x); s[1] += __uint_as_float(v[2 * r].y);
        s[2] += __uint_as_float(v[2 * r].z); s[3] += __uint_as_float(v[2 * r].w);
        s[4] += __uint_as_float(v[2 * r + 1].x); s[5] += __uint_as_float(v[2 * r + 1].y);
        s[6] += __uint_as_float(v[2 * r + 1].z); s[7] += __uint_as_float(v[2 * r + 1].w);
      }
      float zsum = (__uint_as_float(zv[0]) + __uint_as_float(zv[1])) + (__uint_as_float(zv[2]) + __uint_as_float(zv[3]));
      zsum += __shfl_xor_sync(0xffffffffu, zsum, 16);
      stsm4(kvs + w * 512 + lane * 16, pack_bf(s[0], s[1]), pack_bf(s[2], s[3]), pack_bf(s[4], s[5]), pack_bf(s[6], s[7]));
      if (lane < 16) sts16(kvs + 2048 + (w * 16 + lane) * 2, pack_bf(zsum, 0.f));
      TS(6);
    } else {
      float pk[2][2][8];
#pragma unroll
      for (int mt = 0; mt < 2; mt++)
#pragma unroll
        for (int h = 0; h < 2; h++) feat(acc[mt], 4 + 2 * h, wf[h], pk[mt][h]);
      mbar_wait(bars + 8 * MB_GDONE, 0);
      const uint32_t stg1 = sb + OFF_X + 32768;
#pragma unroll
      for (int mt = 0; mt < 2; mt++) {
        const uint32_t sl = stg1 + (mt * 4 + w) * 3072 + lane * 16;
#pragma unroll
        for (int h = 0; h < 2; h++) { v_store(acc[mt], 8 + 2 * h, sl + 2048 + h * 512); phik_store(pk[mt][h], sl + h * 1024); }
        nb_arrive(mt ? NB_ST1 : NB_ST0, 256);
      }
      TS(20);
#pragma unroll
      for (int mt = 0; mt < 2; mt++)
#pragma unroll
        for (int h = 0; h < 2; h++) {
          float pq[8];
          feat(acc[mt], 2 * h, wf[h], pq);
          phiq_pack(pq, eq[mt][h]);
        }
      TS(21);
    }
    nb_sync(NB_KV, 256);
#pragma unroll
    for (int h = 0; h < 2; h++) {
      uint32_t bp[4], bm[4];
      ldsm4t(bp, kvs + (2 * h) * 512 + lane * 16);
      ldsm4t(bm, kvs + (2 * h + 1) * 512 + lane * 16);
      uint32_t zb[4];
#pragma unroll
      for (int i = 0; i < 4; i++) {
        zb[i] = lds32(kvs + 2048 + h * 64 + i * 16 + c * 4);
        if (g & 1) zb[i] = 0x3F803F80u;
      }
#pragma unroll
      for (int mt = 0; mt < 2; mt++) {
        const uint32_t(&e)[8] = eq[mt][h];
        float np[8], nm[8], dp[4], dm[4];
        mma0(dp[0], dp[1], dp[2], dp[3], e[0], e[1], e[2], e[3], zb[0], zb[1]);
        mma0(dm[0], dm[1], dm[2], dm[3], e[4], e[5], e[6], e[7], zb[2], zb[3]);
        mma0(np[0], np[1], np[2], np[3], e[0], e[1], e[2], e[3], bp[0], bp[1]);
        mma0(nm[0], nm[1], nm[2], nm[3], e[4], e[5], e[6], e[7], bm[0], bm[1]);
        mma0(np[4], np[5], np[6], np[7], e[0], e[1], e[2], e[3], bp[2], bp[3]);
        mma0(nm[4], nm[5], nm[6], nm[7], e[4], e[5], e[6], e[7], bm[2], bm[3]);
        float al[2], be[2];
#pragma unroll
        for (int r = 0; r < 2; r++) {
          const float sp = dp[2 * r + 1], sm = dm[2 * r + 1];
          const float inv = rcp(fmaf(dp[2 * r], sm, fmaf(dm[2 * r], sp, 1e-6f * sp * sm)));
          al[r] = sm * inv; be[r] = sp * inv;
        }
        uint32_t o[4];
#pragma unroll
        for (int i = 0; i < 4; i++) {
          const int r = i & 1;
          o[i] = nz(pack_bf(fmaf(np[2 * i], al[r], nm[2 * i] * be[r]), fmaf(np[2 * i + 1], al[r], nm[2 * i + 1] * be[r])));
        }
        st_x(g_o + (size_t)((rt * 4 + wg * 2 + mt) * 32 + hp * 2 + h) * 128 + t, o[0], o[1], o[2], o[3]);
      }
    }
    TS(wg * 16 + 7);
    const int rb = rt * 4 + (hp >> 2), cq = hp & 3;
    const uint4* osrc = g_o + (size_t)(rb * 32 + wg * 16) * 128 + t;
    uint4 af[16];
    for (int it = 0; it < SPIN_MAX; it++) {
      uint32_t m = 0xffffffffu;
#pragma unroll
      for (int i = 0; i < 16; i++) af[i] = ld_x(osrc + i * 128);
#pragma unroll
      for (int i = 0; i < 16; i++) m = min(m, min4(af[i]));
      if (__all_sync(0xffffffffu, m != 0)) break;
    }
    TS(wg * 16 + 8);
#pragma unroll
    for (int j = 0; j < 4; j++) mbar_wait(bars + 8 * (MB_WOFULL + wg * 4 + j), 0);
    nb_sync(NB_BDONE, 384);
    TS(wg * 16 + 9);
    float oc[64];
    WG_FENCE();
#pragma unroll
    for (int j = 0; j < 4; j++) {
      const uint64_t db = mkdesc(sb + wo_addr(wg * 4 + j), 8192, 1024, 1);
#pragma unroll
      for (int k = 0; k < 4; k++) wgmma_rs_n128(oc, af[4 * j + k], db + 128 * k, j | k);
    }
    WG_COMMIT();
    WG_WAIT(0);
    TS(wg * 16 + 10);
    const uint32_t xo = sb + OFF_X + 32768 + wg * 16384 + t * 16, xi = sb + OFF_X + 32768 + (wg ^ 1) * 16384 + t * 16;
    if (wg == 0) {
#pragma unroll
      for (int i = 0; i < 8; i++)
        sts128(xo + i * 2048, __float_as_uint(oc[32 + 4 * i]), __float_as_uint(oc[33 + 4 * i]), __float_as_uint(oc[34 + 4 * i]), __float_as_uint(oc[35 + 4 * i]));
    } else {
#pragma unroll
      for (int i = 0; i < 8; i++) {
        sts128(xo + i * 2048, __float_as_uint(oc[4 * i]), __float_as_uint(oc[1 + 4 * i]), __float_as_uint(oc[2 + 4 * i]), __float_as_uint(oc[3 + 4 * i]));
        oc[4 * i] = oc[32 + 4 * i]; oc[4 * i + 1] = oc[33 + 4 * i]; oc[4 * i + 2] = oc[34 + 4 * i]; oc[4 * i + 3] = oc[35 + 4 * i];
      }
    }
    nb_sync(NB_RED, 256);
    __nv_bfloat16* dst = P.out + (size_t)(rb * 64 + w * 16 + g) * 1024 + cq * 128 + wg * 64 + 2 * c;
#pragma unroll
    for (int i = 0; i < 8; i++) {
      uint4 v = lds128(xi + i * 2048);
      *(uint32_t*)(dst + i * 8) = pack_bf(oc[4 * i] + __uint_as_float(v.x), oc[4 * i + 1] + __uint_as_float(v.y));
      *(uint32_t*)(dst + i * 8 + 8192) = pack_bf(oc[4 * i + 2] + __uint_as_float(v.z), oc[4 * i + 3] + __uint_as_float(v.w));
    }
    TS(wg * 16 + 11);
  }
}

typedef CUresult (*EncodeFn)(CUtensorMap*, CUtensorMapDataType, cuuint32_t, void*, const cuuint64_t*, const cuuint64_t*,
                             const cuuint32_t*, const cuuint32_t*, CUtensorMapInterleave, CUtensorMapSwizzle,
                             CUtensorMapL2promotion, CUtensorMapFloatOOBfill);

}

extern "C" void kernel_launch(void* const* d_in, const int* in_sizes, int n_in, void* d_out, int out_size) {
  (void)in_sizes; (void)n_in; (void)out_size;
  void* fn = nullptr;
  cudaDriverEntryPointQueryResult qr;
  cudaGetDriverEntryPoint("cuTensorMapEncodeTiled", &fn, cudaEnableDefault, &qr);
  EncodeFn enc = (EncodeFn)fn;
  CUtensorMap mx, mw, mo;
  const cuuint32_t es[3] = {1, 1, 1};
  {
    cuuint64_t dims[2] = {512, 2048}, st[1] = {1024};
    cuuint32_t box[2] = {64, 128};
    enc(&mx, CU_TENSOR_MAP_DATA_TYPE_BFLOAT16, 2, d_in[0], dims, st, box, es, CU_TENSOR_MAP_INTERLEAVE_NONE,
        CU_TENSOR_MAP_SWIZZLE_128B, CU_TENSOR_MAP_L2_PROMOTION_L2_128B, CU_TENSOR_MAP_FLOAT_OOB_FILL_NONE);
  }
  {
    cuuint64_t dims[3] = {512, 512, 3}, st[2] = {3072, 1024};
    cuuint32_t box[3] = {32, 64, 3};
    enc(&mw, CU_TENSOR_MAP_DATA_TYPE_BFLOAT16, 3, d_in[1], dims, st, box, es, CU_TENSOR_MAP_INTERLEAVE_NONE,
        CU_TENSOR_MAP_SWIZZLE_64B, CU_TENSOR_MAP_L2_PROMOTION_L2_128B, CU_TENSOR_MAP_FLOAT_OOB_FILL_NONE);
  }
  {
    cuuint64_t dims[3] = {64, 512, 8}, st[2] = {1024, 128};
    cuuint32_t box[3] = {64, 64, 2};
    enc(&mo, CU_TENSOR_MAP_DATA_TYPE_BFLOAT16, 3, d_in[3], dims, st, box, es, CU_TENSOR_MAP_INTERLEAVE_NONE,
        CU_TENSOR_MAP_SWIZZLE_128B, CU_TENSOR_MAP_L2_PROMOTION_L2_128B, CU_TENSOR_MAP_FLOAT_OOB_FILL_NONE);
  }
  Params P;
  P.x = (const __nv_bfloat16*)d_in[0];
  P.wphi = (const __nv_bfloat16*)d_in[2];
  P.wo = (const __nv_bfloat16*)d_in[3];
  P.u = (const __nv_bfloat16*)d_in[4];
  P.logA = (const __nv_bfloat16*)d_in[5];
  P.Aim = (const __nv_bfloat16*)d_in[6];
  P.Cre = (const __nv_bfloat16*)d_in[7];
  P.Cim = (const __nv_bfloat16*)d_in[8];
  P.logdt = (const __nv_bfloat16*)d_in[9];
  P.Dskip = (const __nv_bfloat16*)d_in[10];
  P.out = (__nv_bfloat16*)d_out;
  cudaFuncSetAttribute(fused_kernel, cudaFuncAttributeMaxDynamicSharedMemorySize, SMEM_BYTES);
  fused_kernel<<<NCTA, NTHREADS, SMEM_BYTES>>>(mx, mw, mo, P);
}
```

```cpp
#include <cuda_runtime.h>
#include <cuda_bf16.h>
#include <cuda_fp16.h>
#include <cuda.h>
#include <stdint.h>

#define DBG_TS 0

namespace {

constexpr int NTHREADS = 512;
constexpr int NCTA = 128;
constexpr int OFF_W = 0;
constexpr int OFF_X = 98304;
constexpr int OFF_STG0 = 163840;
constexpr int OFF_U = 188416;
constexpr int U_CH = 4416, U_ODD = 2240, U_PAD = 128;
constexpr int OFF_T = OFF_U + 4 * U_CH;
constexpr int T_CH = 5216;
constexpr int T_D = 0;
constexpr int T_5 = 2144;
constexpr int T_3 = T_5 + 384;
constexpr int T_7 = T_5 + 1024;
constexpr int T_9 = T_7 + 320;
constexpr int T_KC = T_9 + 320;
constexpr int T_ST = T_5 - 1024;
constexpr int OFF_BAR = OFF_T + 4 * T_CH;
constexpr int SMEM_BYTES = OFF_BAR + 256 + 1024;
static_assert(T_KC + 2 * 656 <= T_CH, "table size");
static_assert(SMEM_BYTES <= 232448, "smem");
constexpr int MB_WFULL = 0, MB_XFULL = 8, MB_WOFULL = 12, MB_UFULL = 20, MB_XEMPTY = 21, MB_GDONE = 25  ,
              MB_BDONE = 27, MB_CLOSE = 28;
constexpr int NB_WG0 = 1, NB_KPART = 2, NB_ST0 = 3  , NB_KV = 5, NB_RED = 6, NB_INIT = 7;
constexpr int SPIN_MAX = 1 << 18;

__device__ unsigned g_cnt;
__device__ uint4 g_uT[512 * 256];
__device__ uint4 g_part[16 * 8 * 272];
__device__ uint4 g_o[32 * 32 * 128];
__device__ uint4 g_y[512 * 8 * 32];
#define TS(i) do {} while (0)

__device__ __forceinline__ uint32_t smem_u32(const void* p) { return (uint32_t)__cvta_generic_to_shared(p); }
__device__ __forceinline__ void mbar_init(uint32_t b, int n) {
  asm volatile("mbarrier.init.shared::cta.b64 [%0], %1;" ::"r"(b), "r"(n) : "memory");
}
__device__ __forceinline__ void mbar_expect(uint32_t b, int bytes) {
  asm volatile("mbarrier.arrive.expect_tx.shared::cta.b64 _, [%0], %1;" ::"r"(b), "r"(bytes) : "memory");
}
__device__ __forceinline__ void mbar_arrive(uint32_t b) {
  asm volatile("mbarrier.arrive.shared::cta.b64 _, [%0];" ::"r"(b) : "memory");
}
__device__ __forceinline__ void mbar_wait(uint32_t b, uint32_t parity) {
  uint32_t done = 0;
#pragma unroll 1
  for (int i = 0; i < SPIN_MAX && !done; i++) {
    asm volatile("{\n.reg .pred p;\nmbarrier.try_wait.parity.shared::cta.b64 p, [%1], %2;\nselp.u32 %0, 1, 0, p;\n}\n"
                 : "=r"(done) : "r"(b), "r"(parity) : "memory");
  }
}
__device__ __forceinline__ void nb_sync(int id, int n) { asm volatile("bar.sync %0, %1;" ::"r"(id), "r"(n) : "memory"); }
__device__ __forceinline__ void nb_arrive(int id, int n) { asm volatile("bar.arrive %0, %1;" ::"r"(id), "r"(n) : "memory"); }
__device__ __forceinline__ void tma2d(uint32_t dst, const CUtensorMap* m, uint32_t bar, int c0, int c1) {
  asm volatile("cp.async.bulk.tensor.2d.shared::cluster.global.mbarrier::complete_tx::bytes [%0], [%1, {%3,%4}], [%2];"
               ::"r"(dst), "l"(m), "r"(bar), "r"(c0), "r"(c1) : "memory");
}
__device__ __forceinline__ void tma3d(uint32_t dst, const CUtensorMap* m, uint32_t bar, int c0, int c1, int c2) {
  asm volatile("cp.async.bulk.tensor.3d.shared::cluster.global.mbarrier::complete_tx::bytes [%0], [%1, {%3,%4,%5}], [%2];"
               ::"r"(dst), "l"(m), "r"(bar), "r"(c0), "r"(c1), "r"(c2) : "memory");
}
__device__ __forceinline__ void bulk_g2s(uint32_t dst, const void* src, int bytes, uint32_t bar) {
  asm volatile("cp.async.bulk.shared::cluster.global.mbarrier::complete_tx::bytes [%0], [%1], %2, [%3];"
               ::"r"(dst), "l"(src), "r"(bytes), "r"(bar) : "memory");
}
__device__ __forceinline__ void l2_prefetch(const void* p, int bytes) {
  asm volatile("cp.async.bulk.prefetch.L2.global [%0], %1;" ::"l"(p), "r"(bytes) : "memory");
}
__device__ __forceinline__ uint64_t mkdesc(uint32_t addr, uint32_t lbo, uint32_t sbo, int swz) {
  return (uint64_t)((addr & 0x3FFFF) >> 4) | ((uint64_t)(lbo >> 4) << 16) | ((uint64_t)(sbo >> 4) << 32) |
         ((uint64_t)swz << 62);
}
#define WG_FENCE() asm volatile("wgmma.fence.sync.aligned;" ::: "memory")
#define WG_COMMIT() asm volatile("wgmma.commit_group.sync.aligned;" ::: "memory")
#define WG_WAIT(n) asm volatile("wgmma.wait_group.sync.aligned " #n ";" ::: "memory")

__device__ __forceinline__ void mma(float& d0, float& d1, float& d2, float& d3, uint32_t a0, uint32_t a1, uint32_t a2,
                                    uint32_t a3, uint32_t b0, uint32_t b1) {
  asm volatile("mma.sync.aligned.m16n8k16.row.col.f32.bf16.bf16.f32 {%0,%1,%2,%3},{%4,%5,%6,%7},{%8,%9},{%0,%1,%2,%3};"
               : "+f"(d0), "+f"(d1), "+f"(d2), "+f"(d3)
               : "r"(a0), "r"(a1), "r"(a2), "r"(a3), "r"(b0), "r"(b1));
}
__device__ __forceinline__ void mmac(float (&d)[4], uint32_t a0, uint32_t a1, uint32_t a2, uint32_t a3, uint32_t b0,
                                     uint32_t b1, const float (&c)[4]) {
  asm volatile("mma.sync.aligned.m16n8k16.row.col.f32.bf16.bf16.f32 {%0,%1,%2,%3},{%4,%5,%6,%7},{%8,%9},{%10,%11,%12,%13};"
               : "=f"(d[0]), "=f"(d[1]), "=f"(d[2]), "=f"(d[3])
               : "r"(a0), "r"(a1), "r"(a2), "r"(a3), "r"(b0), "r"(b1), "f"(c[0]), "f"(c[1]), "f"(c[2]), "f"(c[3]));
}
__device__ __forceinline__ void mma0(float& d0, float& d1, float& d2, float& d3, uint32_t a0, uint32_t a1, uint32_t a2,
                                     uint32_t a3, uint32_t b0, uint32_t b1) {
  asm volatile("mma.sync.aligned.m16n8k16.row.col.f32.bf16.bf16.f32 {%0,%1,%2,%3},{%4,%5,%6,%7},{%8,%9},{%10,%10,%10,%10};"
               : "=f"(d0), "=f"(d1), "=f"(d2), "=f"(d3)
               : "r"(a0), "r"(a1), "r"(a2), "r"(a3), "r"(b0), "r"(b1), "f"(0.f));
}
__device__ __forceinline__ uint32_t pack_bf(float lo, float hi) {
  uint32_t r;
  asm("cvt.rn.bf16x2.f32 %0, %1, %2;" : "=r"(r) : "f"(hi), "f"(lo));
  return r;
}
__device__ __forceinline__ float bf_lo(uint32_t w) { return __uint_as_float(w << 16); }
__device__ __forceinline__ float bf_hi(uint32_t w) { return __uint_as_float(w & 0xffff0000u); }
__device__ __forceinline__ float bf_round(float x) { return __bfloat162float(__float2bfloat16_rn(x)); }
__device__ __forceinline__ uint32_t bmax2(uint32_t a, uint32_t b) {
  uint32_t r; asm("max.bf16x2 %0, %1, %2;" : "=r"(r) : "r"(a), "r"(b)); return r;
}
__device__ __forceinline__ uint32_t bmin2(uint32_t a, uint32_t b) {
  uint32_t r; asm("min.bf16x2 %0, %1, %2;" : "=r"(r) : "r"(a), "r"(b)); return r;
}
__device__ __forceinline__ float ex2(float x) { float r; asm("ex2.approx.ftz.f32 %0, %1;" : "=f"(r) : "f"(x)); return r; }
__device__ __forceinline__ float rcp(float x) { float r; asm("rcp.approx.ftz.f32 %0, %1;" : "=f"(r) : "f"(x)); return r; }
__device__ __forceinline__ void ldsm4(uint32_t (&r)[4], uint32_t a) {
  asm volatile("ldmatrix.sync.aligned.m8n8.x4.shared.b16 {%0,%1,%2,%3}, [%4];"
               : "=r"(r[0]), "=r"(r[1]), "=r"(r[2]), "=r"(r[3]) : "r"(a) : "memory");
}
__device__ __forceinline__ uint32_t ldsm1(uint32_t a) {
  uint32_t r;
  asm volatile("ldmatrix.sync.aligned.m8n8.x1.shared.b16 {%0}, [%1];" : "=r"(r) : "r"(a) : "memory");
  return r;
}
__device__ __forceinline__ void ldsm4t(uint32_t (&r)[4], uint32_t a) {
  asm volatile("ldmatrix.sync.aligned.m8n8.x4.trans.shared.b16 {%0,%1,%2,%3}, [%4];"
               : "=r"(r[0]), "=r"(r[1]), "=r"(r[2]), "=r"(r[3]) : "r"(a) : "memory");
}
__device__ __forceinline__ void stsm4(uint32_t a, uint32_t r0, uint32_t r1, uint32_t r2, uint32_t r3) {
  asm volatile("stmatrix.sync.aligned.m8n8.x4.shared.b16 [%0], {%1,%2,%3,%4};"
               ::"r"(a), "r"(r0), "r"(r1), "r"(r2), "r"(r3) : "memory");
}
__device__ __forceinline__ uint32_t lds32(uint32_t a) {
  uint32_t r; asm volatile("ld.shared.u32 %0, [%1];" : "=r"(r) : "r"(a) : "memory"); return r;
}
__device__ __forceinline__ uint32_t lds16(uint32_t a) {
  uint32_t r; asm volatile("{\n.reg .u16 h;\nld.shared.u16 h, [%1];\ncvt.u32.u16 %0, h;\n}\n" : "=r"(r) : "r"(a) : "memory"); return r;
}
__device__ __forceinline__ uint2 lds64(uint32_t a) {
  uint2 r; asm volatile("ld.shared.v2.u32 {%0,%1}, [%2];" : "=r"(r.x), "=r"(r.y) : "r"(a) : "memory"); return r;
}
__device__ __forceinline__ uint4 lds128(uint32_t a) {
  uint4 r;
  asm volatile("ld.shared.v4.u32 {%0,%1,%2,%3}, [%4];" : "=r"(r.x), "=r"(r.y), "=r"(r.z), "=r"(r.w) : "r"(a) : "memory");
  return r;
}
__device__ __forceinline__ void sts32(uint32_t a, uint32_t v) { asm volatile("st.shared.u32 [%0], %1;" ::"r"(a), "r"(v) : "memory"); }
__device__ __forceinline__ void sts16(uint32_t a, uint32_t v) {
  asm volatile("{\n.reg .u16 h;\ncvt.u16.u32 h, %1;\nst.shared.u16 [%0], h;\n}\n" ::"r"(a), "r"(v) : "memory");
}
__device__ __forceinline__ void sts64(uint32_t a, uint32_t x, uint32_t y) {
  asm volatile("st.shared.v2.u32 [%0], {%1,%2};" ::"r"(a), "r"(x), "r"(y) : "memory");
}
__device__ __forceinline__ void sts128(uint32_t a, uint32_t x, uint32_t y, uint32_t z, uint32_t w) {
  asm volatile("st.shared.v4.u32 [%0], {%1,%2,%3,%4};" ::"r"(a), "r"(x), "r"(y), "r"(z), "r"(w) : "memory");
}
__device__ __forceinline__ uint4 ldg_nc(const void* p) {
  uint4 r;
  asm volatile("ld.global.nc.L1::no_allocate.v4.u32 {%0,%1,%2,%3}, [%4];" : "=r"(r.x), "=r"(r.y), "=r"(r.z), "=r"(r.w) : "l"(p));
  return r;
}
__device__ __forceinline__ uint4 ld_x(const uint4* p) {
  uint4 r;
  asm volatile("{\n.reg .b128 t;\nld.relaxed.gpu.global.b128 t, [%4];\nmov.b128 {%0,%1,%2,%3}, t;\n}\n"
               : "=r"(r.x), "=r"(r.y), "=r"(r.z), "=r"(r.w) : "l"(p) : "memory");
  return r;
}
__device__ __forceinline__ uint32_t ld_x32(const uint32_t* p) {
  uint32_t r; asm volatile("ld.relaxed.gpu.global.u32 %0, [%1];" : "=r"(r) : "l"(p) : "memory"); return r;
}
__device__ __forceinline__ void st_x(uint4* p, uint32_t x, uint32_t y, uint32_t z, uint32_t w) {
  asm volatile("{\n.reg .b128 t;\nmov.b128 t, {%1,%2,%3,%4};\nst.relaxed.gpu.global.b128 [%0], t;\n}\n"
               ::"l"(p), "r"(x), "r"(y), "r"(z), "r"(w) : "memory");
}
__device__ __forceinline__ void st_x32(uint32_t* p, uint32_t x) {
  asm volatile("st.relaxed.gpu.global.u32 [%0], %1;" ::"l"(p), "r"(x) : "memory");
}
__device__ __forceinline__ uint32_t nz(uint32_t w) { return max(w, 1u); }
__device__ __forceinline__ uint32_t fu(float x) { return __float_as_uint(x); }
__device__ __forceinline__ float uf(uint32_t x) { return __uint_as_float(x); }

__device__ __forceinline__ void wgmma_ss_n96(float (&d)[48], uint64_t da, uint64_t db, int sc) {
  asm volatile("{\n.reg .pred p;\nsetp.ne.b32 p, %50, 0;\n"
      "wgmma.mma_async.sync.aligned.m64n96k16.f32.bf16.bf16 "
      "{%0,%1,%2,%3,%4,%5,%6,%7,%8,%9,%10,%11,%12,%13,%14,%15,%16,%17,%18,%19,%20,%21,%22,%23,%24,%25,%26,%27,%28,%29,%30,%31,%32,%33,%34,%35,%36,%37,%38,%39,%40,%41,%42,%43,%44,%45,%46,%47}, "
      "%48, %49, p, 1, 1, 0, 1;\n}\n"
      : "+f"(d[0]), "+f"(d[1]), "+f"(d[2]), "+f"(d[3]), "+f"(d[4]), "+f"(d[5]), "+f"(d[6]), "+f"(d[7]),
        "+f"(d[8]), "+f"(d[9]), "+f"(d[10]), "+f"(d[11]), "+f"(d[12]), "+f"(d[13]), "+f"(d[14]), "+f"(d[15]),
        "+f"(d[16]), "+f"(d[17]), "+f"(d[18]), "+f"(d[19]), "+f"(d[20]), "+f"(d[21]), "+f"(d[22]), "+f"(d[23]),
        "+f"(d[24]), "+f"(d[25]), "+f"(d[26]), "+f"(d[27]), "+f"(d[28]), "+f"(d[29]), "+f"(d[30]), "+f"(d[31]),
        "+f"(d[32]), "+f"(d[33]), "+f"(d[34]), "+f"(d[35]), "+f"(d[36]), "+f"(d[37]), "+f"(d[38]), "+f"(d[39]),
        "+f"(d[40]), "+f"(d[41]), "+f"(d[42]), "+f"(d[43]), "+f"(d[44]), "+f"(d[45]), "+f"(d[46]), "+f"(d[47])
      : "l"(da), "l"(db), "r"(sc));
}

__device__ __forceinline__ void wgmma_rs_n128(float (&d)[64], const uint4& a, uint64_t db, int sc) {
  asm volatile("{\n.reg .pred p;\nsetp.ne.b32 p, %69, 0;\n"
      "wgmma.mma_async.sync.aligned.m64n128k16.f32.bf16.bf16 "
      "{%0,%1,%2,%3,%4,%5,%6,%7,%8,%9,%10,%11,%12,%13,%14,%15,%16,%17,%18,%19,%20,%21,%22,%23,%24,%25,%26,%27,%28,%29,%30,%31,%32,%33,%34,%35,%36,%37,%38,%39,%40,%41,%42,%43,%44,%45,%46,%47,%48,%49,%50,%51,%52,%53,%54,%55,%56,%57,%58,%59,%60,%61,%62,%63}, "
      "{%64,%65,%66,%67}, %68, p, 1, 1, 1;\n}\n"
      : "+f"(d[0]), "+f"(d[1]), "+f"(d[2]), "+f"(d[3]), "+f"(d[4]), "+f"(d[5]), "+f"(d[6]), "+f"(d[7]),
        "+f"(d[8]), "+f"(d[9]), "+f"(d[10]), "+f"(d[11]), "+f"(d[12]), "+f"(d[13]), "+f"(d[14]), "+f"(d[15]),
        "+f"(d[16]), "+f"(d[17]), "+f"(d[18]), "+f"(d[19]), "+f"(d[20]), "+f"(d[21]), "+f"(d[22]), "+f"(d[23]),
        "+f"(d[24]), "+f"(d[25]), "+f"(d[26]), "+f"(d[27]), "+f"(d[28]), "+f"(d[29]), "+f"(d[30]), "+f"(d[31]),
        "+f"(d[32]), "+f"(d[33]), "+f"(d[34]), "+f"(d[35]), "+f"(d[36]), "+f"(d[37]), "+f"(d[38]), "+f"(d[39]),
        "+f"(d[40]), "+f"(d[41]), "+f"(d[42]), "+f"(d[43]), "+f"(d[44]), "+f"(d[45]), "+f"(d[46]), "+f"(d[47]),
        "+f"(d[48]), "+f"(d[49]), "+f"(d[50]), "+f"(d[51]), "+f"(d[52]), "+f"(d[53]), "+f"(d[54]), "+f"(d[55]),
        "+f"(d[56]), "+f"(d[57]), "+f"(d[58]), "+f"(d[59]), "+f"(d[60]), "+f"(d[61]), "+f"(d[62]), "+f"(d[63])
      : "r"(a.x), "r"(a.y), "r"(a.z), "r"(a.w), "l"(db), "r"(sc));
}

struct Params {
  const __nv_bfloat16 *x, *wphi, *wo, *u, *logA, *Aim, *Cre, *Cim, *logdt, *Dskip;
  __nv_bfloat16* out;
};

__device__ __forceinline__ uint4 tr_row(const uint4 (&v)[8], int i) {
  uint32_t o[4];
#pragma unroll
  for (int m = 0; m < 4; m++) {
    const uint4 &ra = v[2 * m], &rb = v[2 * m + 1];
    const int k = i >> 1;
    const uint32_t xa = k == 0 ? ra.x : k == 1 ? ra.y : k == 2 ? ra.z : ra.w;
    const uint32_t xb = k == 0 ? rb.x : k == 1 ? rb.y : k == 2 ? rb.z : rb.w;
    o[m] = __byte_perm(xa, xb, (i & 1) ? 0x7632 : 0x5410);
  }
  return make_uint4(o[0], o[1], o[2], o[3]);
}

struct cpx { float r, i; };
__device__ __forceinline__ cpx cmul(cpx a, cpx b) { return {a.r * b.r - a.i * b.i, a.r * b.i + a.i * b.r}; }
__device__ __forceinline__ cpx csq(cpx a) { return {a.r * a.r - a.i * a.i, 2.f * (a.r * a.i)}; }
__device__ __forceinline__ cpx polar(float e, float t) {
  const float m = ex2(e);
  return {m * __cosf(t), m * __sinf(t)};
}
__device__ __forceinline__ float frac(float t) { return t - rintf(t); }

__device__ __forceinline__ void kgen(const Params& P, int d, int half, int lane, uint32_t scr, uint32_t open_bar,
                                     float (&k)[5][4], float& dt, float& k2048) {
  const int g = lane >> 2, c = lane & 3;
  const float TWO_PI = 6.283185307179586f;
  {
    const int o = d * 64 + half * 32 + lane;
    uint32_t la = __ldg((const uint32_t*)P.logA + o), ai = __ldg((const uint32_t*)P.Aim + o);
    uint32_t cr = __ldg((const uint32_t*)P.Cre + o), ci = __ldg((const uint32_t*)P.Cim + o);
    dt = bf_round(expf(__bfloat162float(P.logdt[d])));
    float ks = 0.f;
#pragma unroll 1
    for (int j = 0; j < 2; j++) {
      const float a2 = -(bf_round(expf(bf_lo(la))) * dt) * 1.4426950408889634f;
      const float f = frac((bf_lo(ai) * dt) * 0.15915494309189535f);
      const cpx w64 = polar(a2 * 64.f, frac(f * 64.f) * TWO_PI);
      const cpx we = polar(a2 * 2048.f, frac(f * 2048.f) * TWO_PI);
      ks += bf_lo(cr) * we.r - bf_lo(ci) * we.i;
      sts128(scr + (2 * lane + j) * 16, fu(a2), fu(f * TWO_PI), fu(w64.r), fu(w64.i));
      sts64(scr + 1024 + (2 * lane + j) * 8, __byte_perm(cr, ci, 0x5410), fu(frac(f * 128.f) * TWO_PI));
      la >>= 16; ai >>= 16; cr >>= 16; ci >>= 16;
    }
#pragma unroll
    for (int o2 = 16; o2; o2 >>= 1) ks += __shfl_xor_sync(0xffffffffu, ks, o2);
    k2048 = ks;
    __syncwarp();
  }
  const float pg = (float)g;
  const float n2 = (float)(2 + (g & 1)), m2 = (float)(g & 6), p2 = 128.f * n2 + m2;
  const float n3 = (float)(4 + (g & 3)), m3 = (float)(g & 4), p3 = 128.f * n3 + m3;
  uint32_t Q[8][14];
#pragma unroll 1
  for (int s = 0; s < 8; s++) {
    uint32_t o[14];
#pragma unroll
    for (int h = 0; h < 2; h++) {
      const uint4 q = lds128(scr + (8 * s + 4 * h + c) * 16);
      const uint2 cw = lds64(scr + 1024 + (8 * s + 4 * h + c) * 8);
      const float a2 = uf(q.x), f = uf(q.y), f128 = uf(cw.y);
      const cpx w64 = {uf(q.z), uf(q.w)};
      const cpx C = {bf_lo(cw.x), bf_hi(cw.x)};
      const cpx d1 = polar(a2 * pg, f * pg);
      const cpx t2 = polar(a2 * p2, fmaf(f128, n2, f * m2));
      const cpx t3 = polar(a2 * p3, fmaf(f128, n3, f * m3));
      const cpx s8 = csq(csq(csq(d1)));
      const cpx z = cmul(s8, w64);
      const cpx a0 = cmul(C, s8), a1 = cmul(C, z);
      const cpx t1 = cmul(d1, csq(w64));
      const cpx t4 = csq(csq(csq(csq(z))));
      o[2 * h] = pack_bf(a0.r, -a0.i);
      o[2 * h + 1] = pack_bf(a1.r, -a1.i);
      o[4 + h] = pack_bf(d1.r, d1.i);
      o[6 + h] = pack_bf(t1.r, t1.i);
      o[8 + h] = pack_bf(t2.r, t2.i);
      o[10 + h] = pack_bf(t3.r, t3.i);
      o[12 + h] = pack_bf(t4.r, t4.i);
    }
#define KQ(i) case i: _Pragma("unroll") for (int e = 0; e < 14; e++) asm volatile("mov.b32 %0, %1;" : "=r"(Q[i][e]) : "r"(o[e])); break;
    switch (s) { KQ(0) KQ(1) KQ(2) KQ(3) KQ(4) KQ(5) KQ(6) default: KQ(7) }
#undef KQ
  }
  mbar_wait(open_bar, 0);
#pragma unroll
  for (int j = 0; j < 5; j++) mma0(k[j][0], k[j][1], k[j][2], k[j][3], Q[0][0], Q[0][1], Q[0][2], Q[0][3], Q[0][4 + 2 * j], Q[0][5 + 2 * j]);
#pragma unroll
  for (int s = 1; s < 8; s++)
#pragma unroll
    for (int j = 0; j < 5; j++) mma(k[j][0], k[j][1], k[j][2], k[j][3], Q[s][0], Q[s][1], Q[s][2], Q[s][3], Q[s][4 + 2 * j], Q[s][5 + 2 * j]);
}

__device__ __forceinline__ void build_tables(uint32_t tb, int lane, float (&k)[5][4], float k2048) {
  const int g = lane >> 2, c = lane & 3;
  const uint32_t kc = tb + T_KC + 16;
  {
    const uint32_t a0 = kc + 16 * g + 4 * c, a2 = kc + 2 * (256 + 4 * g + c);
    const uint32_t a3 = kc + 2 * (384 + 2 * g + 64 * (c & 1) + (c >> 1)), a4 = kc + 2 * (512 + g + 32 * c);
#pragma unroll
    for (int r = 0; r < 2; r++) {
      sts32(a0 + 128 * r, pack_bf(k[0][2 * r], k[0][2 * r + 1]));
      sts32(a0 + 128 * r + 256, pack_bf(k[1][2 * r], k[1][2 * r + 1]));
      const uint32_t w2 = pack_bf(k[2][2 * r], k[2][2 * r + 1]);
      const uint32_t w3 = pack_bf(k[3][2 * r], k[3][2 * r + 1]);
      const uint32_t w4 = pack_bf(k[4][2 * r], k[4][2 * r + 1]);
      sts16(a2 + 64 * r, w2); sts16(a2 + 64 * r + 128, w2 >> 16);
      sts16(a3 + 32 * r, w3); sts16(a3 + 32 * r + 64, w3 >> 16);
      sts16(a4 + 16 * r, w4); sts16(a4 + 16 * r + 32, w4 >> 16);
    }
  }
  if (lane == 0) { sts16(kc + 2 * 640, pack_bf(k2048, 0.f)); sts16(kc - 2, 0); }
  __syncwarp();
  const uint32_t td = tb + T_D + 32;
  {
    const uint4 v = lds128(kc + 16 * lane);
    const uint32_t pv = lds16(kc + 16 * lane - 2);
    sts128(td + 32 * lane, __byte_perm(v.x, pv, 0x5410), __byte_perm(v.x, v.x, 0x1032), __byte_perm(v.y, v.x, 0x7610),
           __byte_perm(v.y, v.y, 0x1032));
    sts128(td + 32 * lane + 16, __byte_perm(v.z, v.y, 0x7610), __byte_perm(v.z, v.z, 0x1032),
           __byte_perm(v.w, v.z, 0x7610), __byte_perm(v.w, v.w, 0x1032));
  }
  {
    const uint2 v = lds64(kc + 512 + 8 * lane);
    const uint32_t k4 = lds16(kc + 512 + 8 * lane + 8);
    const uint32_t pv = lds16(kc + (lane == 0 ? 510 : 512 + 8 * lane));
    const uint32_t k22 = __byte_perm(v.y, v.y, 0x1010);
    sts128(td + 1024 + 32 * lane, __byte_perm(v.x, pv, 0x5410), __byte_perm(v.x, v.x, 0x1010),
           __byte_perm(v.x, v.x, 0x1032), __byte_perm(v.y, v.x, 0x7610));
    sts128(td + 1024 + 32 * lane + 16, k22, k22, __byte_perm(v.y, v.y, 0x1032), __byte_perm(k4, v.y, 0x7610));
  }
  {
    const uint32_t kk = lds16(kc + 2 * 384);
    const uint32_t w = lane < 3 ? (kk | (kk << 16)) : (lane == 3 ? (kk << 16) : 0u);
    if (lane < 24) sts32(td + 4 * (lane < 16 ? 512 + lane : lane - 24), w);
    const uint32_t lo_ = lds16(kc + 2 * 511), le_ = lds16(kc + 2 * 512);
    const uint32_t ja = tb + T_5 + (lane < 16 ? 4 * lane : 256 + 4 * lane);
    sts32(ja, lane == 16 ? (le_ << 16) : 0u);
    sts32(ja + 384, lane == 16 ? (lo_ << 16) : 0u);
    sts32(tb + (lane < 16 ? T_7 : T_9 - 64) + 4 * lane, 0u);
  }
#pragma unroll
  for (int s = 0; s < 2; s++) {
    const uint32_t b = kc + 2 * (s ? 512 : 384) + 8 * lane;
    const uint2 v = lds64(b);
    uint32_t em = lds16(b - 2), e0 = v.x;
    const uint32_t e4 = lds16(b + 8);
    if (lane == 0) { em = 0; e0 = 0; }
    sts64(tb + (s ? T_7 : T_3) + 64 + 8 * lane, __byte_perm(v.x, em, 0x5432), __byte_perm(v.y, v.x, 0x7632));
    sts64(tb + (s ? T_9 : T_5) + 64 + 8 * lane, __byte_perm(v.y, e0, 0x5410), __byte_perm(e4, v.y, 0x5410));
  }
  __syncwarp();
}

__device__ __forceinline__ uint32_t box2w(int lo, int n, int o) {
  return ((unsigned)(o - lo) < (unsigned)n ? 0x3F80u : 0u) | ((unsigned)(o + 1 - lo) < (unsigned)n ? 0x3F800000u : 0u);
}

__device__ __forceinline__ void conv_channel(uint32_t ub, uint32_t tb, int lane, uint4* ydst, uint32_t go_bar) {
  const int g = lane >> 2, c = lane & 3, x = g - 2 * c;
  const uint32_t st = tb + T_ST + lane * 8;
  const int mi = lane >> 3;
  const uint32_t qa = ub + U_PAD + 16 * (lane & 7) + ((mi == 0 || mi == 3) ? U_ODD : 0) - (mi == 0 ? 16 : 0);
  const uint32_t kv = lds16(tb + T_KC + 16 + 2 * 512);
  {
    const uint32_t hb = ub + U_PAD + (mi & 1) * U_ODD + 16 * ((lane >> 4) + (lane & 7)) - 16;
    const int oh = c < 2 ? 8 + 2 * c : 2 * c - 8;
    const uint32_t bx0 = box2w(g - 4, 9, 2 * c), bx1 = box2w(g - 3, 7, 2 * c), bx2 = box2w(g - 4, 9, oh), bx3 = box2w(g - 3, 7, oh);
    uint32_t f7[9], f9a[9], f9b[9];
    const uint32_t fa = tb + T_7 + 4 * (8 + x);
#pragma unroll
    for (int m = 0; m < 9; m++) {
      f7[m] = lds32(fa + 32 * m);
      f9b[m] = lds32(fa + 320 + 32 * m);
      f9a[m] = lds32(fa + 316 + 32 * m);
    }
    mbar_wait(go_bar, 0);
    uint32_t z09[8], z07[8], zm9[8], zm7[8];
#pragma unroll
    for (int i = 0; i < 8; i++) {
      uint32_t h[4];
      ldsm4(h, hb + 128 * i);
      float y0, y1, y2, y3, w0, w1, w2, w3;
      mma0(y0, y1, y2, y3, bx0, bx1, bx2, bx3, h[2], c < 2 ? h[3] : h[1]);
      mma0(w0, w1, w2, w3, bx0, bx1, bx2, bx3, h[1], c < 2 ? h[2] : h[0]);
      z09[i] = pack_bf(y0, y1); z07[i] = pack_bf(y2, y3);
      zm9[i] = pack_bf(w0, w1); zm7[i] = pack_bf(w2, w3);
    }
    float a[4][2][4];
#pragma unroll
    for (int kap = 0; kap < 4; kap++)
#pragma unroll
      for (int sg = 0; sg < 2; sg++)
#pragma unroll
        for (int bk = 3; bk >= kap; bk--) {
          const int m = 2 * (bk - kap) + 1;
          float(&a0)[4] = a[bk][0];
          float(&a1)[4] = a[bk][1];
          if (sg == 0 && kap == 0) {
            mma0(a0[0], a0[1], a0[2], a0[3], f9a[m], f9a[m + 1], f9a[m - 1], f9a[m], z09[0], z09[1]);
            mma0(a1[0], a1[1], a1[2], a1[3], f9b[m], f9b[m + 1], f9b[m - 1], f9b[m], zm9[0], zm9[1]);
          } else if (sg == 0) {
            mma(a0[0], a0[1], a0[2], a0[3], f9a[m], f9a[m + 1], f9a[m - 1], f9a[m], z09[2 * kap], z09[2 * kap + 1]);
            mma(a1[0], a1[1], a1[2], a1[3], f9b[m], f9b[m + 1], f9b[m - 1], f9b[m], zm9[2 * kap], zm9[2 * kap + 1]);
          } else {
            mma(a0[0], a0[1], a0[2], a0[3], f7[m], f7[m + 1], f7[m - 1], f7[m], zm7[2 * kap], zm7[2 * kap + 1]);
            mma(a1[0], a1[1], a1[2], a1[3], f7[m], f7[m + 1], f7[m - 1], f7[m], z07[2 * kap], z07[2 * kap + 1]);
          }
        }
#pragma unroll
    for (int bk = 0; bk < 4; bk++) {
      sts64(st + 256 * (8 + 2 * bk), pack_bf(a[bk][0][0], a[bk][0][1]), pack_bf(a[bk][1][0], a[bk][1][1]));
      sts64(st + 256 * (9 + 2 * bk), pack_bf(a[bk][0][2], a[bk][0][3]), pack_bf(a[bk][1][2], a[bk][1][3]));
    }
  }
  {
    const int oh = c < 3 ? 2 * c : -10;
    const uint32_t bx0 = box2w(g - 10, 5, 2 * c - 8), bx1 = box2w(g - 5, 3, 2 * c - 8), bx2 = box2w(g - 10, 5, oh), bx3 = box2w(g - 5, 3, oh);
    const uint32_t lb0 = ((unsigned)(x + 5) < 2u ? kv : 0u) | ((unsigned)(x + 4) < 2u ? kv << 16 : 0u);
    const uint32_t lb1 = ((unsigned)(x - 3) < 2u ? kv : 0u) | ((unsigned)(x - 4) < 2u ? kv << 16 : 0u);
    const int q0 = g - 1, q1 = c < 3 ? g : g - 2;
    uint32_t y0a = ub + U_PAD + (q0 & 1) * U_ODD + 16 * (q0 >> 1) + 4 * c;
    uint32_t y1a = ub + U_PAD + (q1 & 1) * U_ODD + 16 * (q1 >> 1) + 4 * c;
    uint2 a5[10], a3[10];
    const uint32_t aa = tb + T_5 + 4 * (8 + 2 * g - 2 * c);
#pragma unroll
    for (int m = 0; m < 10; m++) { a5[m] = lds64(aa + 32 * m); a3[m] = lds64(aa + 384 + 32 * m); }
    float T[6][4];
#pragma unroll
    for (int i = 0; i < 6; i++) T[i][0] = T[i][1] = T[i][2] = T[i][3] = 0.f;
    uint32_t x5[2] = {0, 0}, x3[2] = {0, 0};
#pragma unroll 1
    for (int kap = -1; kap < 13; kap++) {
      float yn[2][4];
      if (kap < 11) {
#pragma unroll
        for (int hh = 0; hh < 2; hh++)
          mma0(yn[hh][0], yn[hh][1], yn[hh][2], yn[hh][3], bx0, bx1, bx2, bx3, lds32(y0a + 64 * hh), lds32(y1a + 64 * hh));
      }
      if (kap > 0) sts64(st + 256 * (kap + 3), pack_bf(T[0][0], T[0][1]), pack_bf(T[0][2], T[0][3]));
      if (kap >= 0) {
#pragma unroll
        for (int i = 0; i < 5; i++)
          if (kap + i < 12) mmac(T[i], a5[2 * i + 1].x, a5[2 * i + 1].y, a5[2 * i].x, a5[2 * i].y, x5[0], x5[1], T[i + 1]);
      }
      if (kap < 7) {
        uint32_t h[4];
        ldsm4(h, qa + 128 * (kap + 1));
        const uint2 v = lds64(st + 256 * (kap + 9));
        const float ci[4] = {bf_lo(v.x), bf_hi(v.x), bf_lo(v.y), bf_hi(v.y)};
        mmac(T[5], h[0], h[1], h[2], h[3], lb0, lb1, ci);
      }
      if (kap >= 0) {
#pragma unroll
        for (int i = 0; i < 5; i++)
          if (kap + i < 12) mma(T[i][0], T[i][1], T[i][2], T[i][3], a3[2 * i + 1].x, a3[2 * i + 1].y, a3[2 * i].x, a3[2 * i].y, x3[0], x3[1]);
      }
#pragma unroll
      for (int hh = 0; hh < 2; hh++) { x5[hh] = pack_bf(yn[hh][0], yn[hh][1]); x3[hh] = pack_bf(yn[hh][2], yn[hh][3]); }
      y0a += 128; y1a += 128;
    }
  }
  {
    uint32_t F[66];
    const uint32_t fa = tb + T_D + 32 + 4 * x;
#pragma unroll
    for (int m = 0; m < 66; m++) F[m] = lds32(fa + 32 * m);
    float T[5][4];
#pragma unroll
    for (int i = 0; i < 5; i++) T[i][0] = T[i][1] = T[i][2] = T[i][3] = 0.f;
    uint32_t qe[5][4], held[2] = {0, 0};
    uint32_t qp = qa + 128 * 15;
    uint32_t hp1 = ub + U_PAD + 16 * (lane & 7) + 128 * 15;
    ldsm4(qe[0], qp);
#pragma unroll 1
    for (int be = 15; be >= 0; be--) {
      uint32_t h0[4];
#pragma unroll
      for (int i = 0; i < 4; i++) {
        h0[i] = ldsm1(hp1 - 16 - 32 * i);
        ldsm4(qe[i + 1], qp - 32 - 32 * i);
      }
      float ci[4] = {0.f, 0.f, 0.f, 0.f};
      if (be >= 4) {
        const uint2 v = lds64(st + 256 * be);
        ci[0] = bf_lo(v.x); ci[1] = bf_hi(v.x); ci[2] = bf_lo(v.y); ci[3] = bf_hi(v.y);
      }
#pragma unroll
      for (int k = 4; k >= 1; k--)
        if (be + k <= 15) mmac(T[k], qe[0][0], qe[0][1], qe[0][2], qe[0][3], F[16 * k + 1], F[16 * k], T[k - 1]);
      mmac(T[0], qe[0][0], qe[0][1], qe[0][2], qe[0][3], F[1], F[0], ci);
#pragma unroll
      for (int i = 1; i < 8; i++) {
        const int e = i >> 1;
        const uint32_t a0 = (i & 1) ? qe[e + 1][3] : qe[e][0], a1 = (i & 1) ? h0[e] : qe[e][1];
        const uint32_t a2 = (i & 1) ? h0[e] : qe[e][2], a3 = (i & 1) ? qe[e][0] : qe[e][3];
#pragma unroll
        for (int k = 3; k >= 0; k--)
          if (k == 0 || be + k <= 15) mma(T[k][0], T[k][1], T[k][2], T[k][3], a0, a1, a2, a3, F[16 * k + 2 * i + 1], F[16 * k + 2 * i]);
        if (i == 2) {
          const uint32_t w0 = pack_bf(T[4][0], T[4][1]), w1 = pack_bf(T[4][2], T[4][3]);
          if (be <= 10 && !(be & 1)) st_x(ydst + (be + 4) * 16, nz(w0), w1, held[0], held[1]);
          held[0] = w0; held[1] = w1;
        }
      }
#pragma unroll
      for (int i = 0; i < 4; i++) qe[0][i] = qe[4][i];
      qp -= 128; hp1 -= 128;
    }
#pragma unroll
    for (int B = 1; B >= 0; B--)
      st_x(ydst + B * 32, nz(pack_bf(T[2 * B][0], T[2 * B][1])), pack_bf(T[2 * B][2], T[2 * B][3]),
           pack_bf(T[2 * B + 1][0], T[2 * B + 1][1]), pack_bf(T[2 * B + 1][2], T[2 * B + 1][3]));
  }
}

__device__ __forceinline__ void feat(const float (&acc)[48], int j0, const uint32_t (&wf)[4], uint32_t* w) {
  const uint32_t a0 = pack_bf(acc[4 * j0], acc[4 * j0 + 1]), a1 = pack_bf(acc[4 * j0 + 2], acc[4 * j0 + 3]);
  const uint32_t a2 = pack_bf(acc[4 * j0 + 4], acc[4 * j0 + 5]), a3 = pack_bf(acc[4 * j0 + 6], acc[4 * j0 + 7]);
  float p[8];
  mma0(p[0], p[1], p[2], p[3], a0, a1, a2, a3, wf[0], wf[1]);
  mma0(p[4], p[5], p[6], p[7], a0, a1, a2, a3, wf[2], wf[3]);
  w[0] = pack_bf(p[0], p[2]); w[1] = pack_bf(p[1], p[3]); w[2] = pack_bf(p[4], p[6]); w[3] = pack_bf(p[5], p[7]);
}
__device__ __forceinline__ void dual_softmax(const uint32_t* w, uint32_t* e) {
  const float L = 1.4426950408889634f;
  uint32_t mx = bmax2(bmax2(w[0], w[1]), bmax2(w[2], w[3]));
  uint32_t mn = bmin2(bmin2(w[0], w[1]), bmin2(w[2], w[3]));
  mx = bmax2(mx, __shfl_xor_sync(0xffffffffu, mx, 1));
  mn = bmin2(mn, __shfl_xor_sync(0xffffffffu, mn, 1));
  mx = bmax2(mx, __shfl_xor_sync(0xffffffffu, mx, 2));
  mn = bmin2(mn, __shfl_xor_sync(0xffffffffu, mn, 2));
  const float mx0 = __fmul_rn(bf_lo(mx), L), mx1 = __fmul_rn(bf_hi(mx), L);
  const float mn0 = __fmul_rn(bf_lo(mn), L), mn1 = __fmul_rn(bf_hi(mn), L);
  float ep[2][4], em[2][4];
#pragma unroll
  for (int i = 0; i < 4; i++) {
    const float x0 = __fmul_rn(bf_lo(w[i]), L), x1 = __fmul_rn(bf_hi(w[i]), L);
    ep[0][i] = ex2(__fsub_rn(x0, mx0)); em[0][i] = ex2(__fsub_rn(mn0, x0));
    ep[1][i] = ex2(__fsub_rn(x1, mx1)); em[1][i] = ex2(__fsub_rn(mn1, x1));
  }
  __half2 sp = __floats2half2_rn((ep[0][0] + ep[0][1]) + (ep[0][2] + ep[0][3]), (ep[1][0] + ep[1][1]) + (ep[1][2] + ep[1][3]));
  __half2 sm = __floats2half2_rn((em[0][0] + em[0][1]) + (em[0][2] + em[0][3]), (em[1][0] + em[1][1]) + (em[1][2] + em[1][3]));
  sp = __hadd2(sp, __shfl_xor_sync(0xffffffffu, sp, 1));
  sm = __hadd2(sm, __shfl_xor_sync(0xffffffffu, sm, 1));
  sp = __hadd2(sp, __shfl_xor_sync(0xffffffffu, sp, 2));
  sm = __hadd2(sm, __shfl_xor_sync(0xffffffffu, sm, 2));
  const float rp[2] = {rcp(__low2float(sp)), rcp(__high2float(sp))}, rm[2] = {rcp(__low2float(sm)), rcp(__high2float(sm))};
#pragma unroll
  for (int i = 0; i < 4; i++) {
    const int r = i & 1, k = i & 2;
    e[i] = pack_bf(ep[r][k] * rp[r], ep[r][k + 1] * rp[r]);
    e[4 + i] = pack_bf(em[r][k] * rm[r], em[r][k + 1] * rm[r]);
  }
}
__device__ __forceinline__ uint32_t wo_addr(int kb) { return OFF_W + kb * 16384; }

__global__ void __launch_bounds__(NTHREADS, 1)
fused_kernel(const __grid_constant__ CUtensorMap mx, const __grid_constant__ CUtensorMap mw,
             const __grid_constant__ CUtensorMap mo, const Params P) {
  extern __shared__ uint8_t smem_raw[];
  const uint32_t sb = (smem_u32(smem_raw) + 1023u) & ~1023u;
  const uint32_t bars = sb + OFF_BAR;
  const int tid = threadIdx.x, lane = tid & 31;
  const int warp = __shfl_sync(0xffffffffu, tid >> 5, 0);
  const int b = blockIdx.x, oct = b >> 3, i8 = b & 7;
  const int rt = oct < 8 ? oct : 15 - oct;
  const int hp = (oct >> 3) * 8 + i8;

  if (warp == 12) {
    if (lane < 29) mbar_init(bars + 8 * lane, lane < MB_XEMPTY ? 1 : (lane < MB_CLOSE ? 4 : 12));
    asm volatile("fence.mbarrier_init.release.cluster;" ::: "memory");
    asm volatile("bar.arrive 0, 512;" ::: "memory");
    if (lane == 0) {
#pragma unroll 1
      for (int kb = 0; kb < 8; kb++) {
        mbar_expect(bars + 8 * (MB_WFULL + kb), 12288);
        tma3d(sb + OFF_W + kb * 12288, &mw, bars + 8 * (MB_WFULL + kb), hp * 32, kb * 64, 0);
        if (kb < 4) {
          mbar_expect(bars + 8 * (MB_XFULL + kb), 16384);
          tma2d(sb + OFF_X + kb * 16384, &mx, bars + 8 * (MB_XFULL + kb), kb * 64, rt * 256);
        }
      }
    }
  } else {
    asm volatile("bar.sync 0, 512;" ::: "memory");
  }

  if (warp >= 12) {
    __syncwarp();
    asm volatile("setmaxnreg.dec.sync.aligned.u32 32;");
    if (warp == 12) {
      if (lane == 0) {
        l2_prefetch(P.x + (size_t)(rt * 256 + hp * 16) * 512, 16384);
        l2_prefetch(P.wo + (size_t)b * 2048, 4096);
#pragma unroll 1
        for (int n = 0; n < 17; n++) {
          if (n < 16) mbar_wait(bars + 8 * (MB_XEMPTY + (n & 3)), (n >> 2) & 1);
          if (n < 12) {
            const int m = n + 4;
            mbar_expect(bars + 8 * (MB_XFULL + (n & 3)), 16384);
            tma2d(sb + OFF_X + (n & 3) * 16384, &mx, bars + 8 * (MB_XFULL + (n & 3)), (m & 7) * 64, rt * 256 + (m >> 3) * 128);
          }
          if (n >= 9) {
            const int w0 = (0x75436210u >> (4 * (n - 9))) & 7;
            const int col = (hp & 3) * 128 + (w0 >> 2) * 64;
            mbar_expect(bars + 8 * (MB_WOFULL + w0), 16384);
            tma2d(sb + wo_addr(w0), &mo, bars + 8 * (MB_WOFULL + w0), col, w0 * 64);
            tma2d(sb + wo_addr(w0) + 8192, &mo, bars + 8 * (MB_WOFULL + w0), col ^ 64, w0 * 64);
          }
        }
      }
    } else {
      unsigned target = 0;
      if (tid == 416) target = (ld_x32(&g_cnt) & ~(unsigned)(NCTA - 1)) + NCTA;
      const int t = tid - 416;
      uint4* po = g_o + (size_t)(rt * 4 * 32 + hp * 2) * 128;
      uint4* py = g_y + (size_t)b * 1024;
      uint4* pp = g_part + (size_t)(hp * 8 + rt) * 272;
#pragma unroll 1
      for (int i = t; i < 1024; i += 96) {
        st_x(po + (i >> 8) * 4096 + (i & 255), 0, 0, 0, 0);
        st_x(py + i, 0, 0, 0, 0);
        if (i < 272) st_x(pp + i, 0, 0, 0, 0);
      }
      nb_sync(NB_INIT, 224);
      if (tid == 416) {
        asm volatile("fence.proxy.async.global;" ::: "memory");
        asm volatile("red.release.gpu.global.add.u32 [%0], 1;" ::"l"(&g_cnt) : "memory");
#pragma unroll 1
        for (int i = 0; i < SPIN_MAX; i++) {
          unsigned v;
          asm volatile("ld.acquire.gpu.global.u32 %0, [%1];" : "=r"(v) : "l"(&g_cnt) : "memory");
          if ((int)(v - target) >= 0) break;
          __nanosleep(100);
        }
        asm volatile("fence.proxy.async.global;" ::: "memory");
        mbar_expect(bars + 8 * MB_UFULL, 16384);
#pragma unroll 1
        for (int i = 0; i < 8; i++)
          bulk_g2s(sb + OFF_U + (i >> 1) * U_CH + (i & 1) * U_ODD + U_PAD, g_uT + (size_t)(b * 8 + i) * 128, 2048,
                   bars + 8 * MB_UFULL);
      }
    }
    return;
  }

  asm volatile("setmaxnreg.inc.sync.aligned.u32 160;");
  const int wg = warp >> 2, w = warp & 3, t = tid & 127;
  const int g = lane >> 2, c = lane & 3;
  const uint32_t tb = sb + OFF_T + w * T_CH;
  if (wg == 0) {
    const int r0 = oct * 128 + w * 32 + (lane >> 3) * 8, c0 = i8 * 64 + (lane & 7) * 8;
    uint4 row[8];
#pragma unroll
    for (int i = 0; i < 8; i++) row[i] = ldg_nc(P.u + (size_t)(r0 + i) * 512 + c0);
    const int q = r0 >> 3;
    uint4* dst = g_uT + (size_t)c0 * 256 + (q & 1) * 128 + (q >> 1);
#pragma unroll
    for (int i = 0; i < 8; i++) dst[i * 256] = tr_row(row, i);
    asm volatile("fence.proxy.async.global;" ::: "memory");
    nb_arrive(NB_INIT, 224);
    TS(1);
  } else {
    const int d = b * 4 + w;
    float k[5][4], dt, k2048;
    kgen(P, d, wg - 1, lane, sb + OFF_STG0 + (warp - 4) * 1536, bars + 8 * MB_GDONE, k, dt, k2048);
    if (lane == 0 && (fu(k[0][0]) & fu(k[1][0]) & fu(k[2][0]) & fu(k[3][0]) & fu(k[4][0])) != 0xffffffffu)
      mbar_arrive(bars + 8 * MB_CLOSE);
    if (wg == 2) {
      const uint32_t ub = sb + OFF_U + w * U_CH;
      TS(34);
      const float dsk = __bfloat162float(P.Dskip[d]);
      if (lane < 16) sts128(ub + (lane >> 3) * U_ODD + (lane & 7) * 16, 0, 0, 0, 0);
      nb_sync(NB_KPART, 256);
      const float sc = 2.f * dt;
#pragma unroll
      for (int j = 0; j < 5; j++) {
        const uint4 v = lds128(tb + j * 512 + lane * 16);
        k[j][0] = (k[j][0] + uf(v.x)) * sc; k[j][1] = (k[j][1] + uf(v.y)) * sc;
        k[j][2] = (k[j][2] + uf(v.z)) * sc; k[j][3] = (k[j][3] + uf(v.w)) * sc;
      }
      k2048 = (k2048 + uf(lds32(tb + 2560))) * sc;
      if (lane == 0) k[0][0] += dsk;
      __syncwarp();
      build_tables(tb, lane, k, k2048);
      TS(35);
      mbar_wait(bars + 8 * MB_UFULL, 0);
      conv_channel(ub, tb, lane, g_y + (size_t)d * 256 + lane, bars + 8 * (MB_GDONE + 1));
      if (lane == 0) mbar_arrive(bars + 8 * MB_BDONE);
      TS(37);
      const int lam = w * 8 + g;
      const uint4* src = g_y + (size_t)(oct * 32 + c * 8) * 256 + i8 * 32 + lam;
      uint4 v[8];
#pragma unroll 1
      for (int it = 0; it < SPIN_MAX; it++) {
        uint32_t m = 0xffffffffu;
#pragma unroll
        for (int i = 0; i < 8; i++) v[i] = ld_x(src + i * 256);
#pragma unroll
        for (int i = 0; i < 8; i++) m = min(m, v[i].x);
        if (__all_sync(0xffffffffu, m != 0)) break;
      }
      __nv_bfloat16* dst = P.out + (size_t)(i8 * 256 + (lam >> 2) * 16 + (lam & 3) * 2) * 1024 + 512 + oct * 32 + c * 8;
#pragma unroll
      for (int i = 0; i < 8; i++) *(uint4*)(dst + (size_t)((i >> 2) * 128 + ((i >> 1) & 1) * 8 + (i & 1)) * 1024) = tr_row(v, i);
      TS(38);
      return;
    }
#pragma unroll
    for (int j = 0; j < 5; j++) sts128(tb + j * 512 + lane * 16, fu(k[j][0]), fu(k[j][1]), fu(k[j][2]), fu(k[j][3]));
    if (lane == 0) sts32(tb + 2560, fu(k2048));
    nb_arrive(NB_KPART, 256);
    mbar_wait(bars + 8 * MB_CLOSE, 0);
    TS(17);
  }

  uint32_t wf[2][4];
  {
    const unsigned short* wp = (const unsigned short*)P.wphi + hp * 512 + c * 32 + g;
#pragma unroll
    for (int h = 0; h < 2; h++)
#pragma unroll
      for (int i = 0; i < 4; i++) {
        const int o = h * 256 + (i & 1) * 128 + (i >> 1) * 8;
        wf[h][i] = __byte_perm(__ldg(wp + o), __ldg(wp + o + 16), 0x5410);
      }
  }
  float acc[2][48];
#pragma unroll 1
  for (int kb = 0; kb < 8; kb++) {
    const int n = wg * 8 + kb;
    mbar_wait(bars + 8 * (MB_WFULL + kb), 0);
    mbar_wait(bars + 8 * (MB_XFULL + (n & 3)), (n >> 2) & 1);
    if (kb == 0) TS(wg * 16 + 2);
    const uint64_t da = mkdesc(sb + OFF_X + (n & 3) * 16384, 16, 1024, 1);
    const uint64_t db = mkdesc(sb + OFF_W + kb * 12288, 4096, 512, 2);
    WG_FENCE();
#pragma unroll
    for (int k = 0; k < 4; k++) {
      wgmma_ss_n96(acc[0], da + 2 * k, db + 64 * k, kb | k);
      wgmma_ss_n96(acc[1], da + 2 * k + 512, db + 64 * k, kb | k);
    }
    WG_COMMIT();
    WG_WAIT(1);
    if (kb > 0 && lane == 0) mbar_arrive(bars + 8 * (MB_XEMPTY + ((n - 1) & 3)));
  }
  WG_WAIT(0);
  if (lane == 0) {
    mbar_arrive(bars + 8 * (MB_GDONE + wg));
    mbar_arrive(bars + 8 * (MB_XEMPTY + 3));
  }
  TS(wg * 16 + 3);

  uint32_t pw[32], eq[32];
#pragma unroll
  for (int u = 0; u < 4; u++)
#pragma unroll
    for (int h = 0; h < 2; h++) feat(acc[u & 1], (u < 2 ? 4 : 0) + 2 * h, wf[h], pw + 8 * u + 4 * h);
  {
    uint32_t all = 0xffffffffu;
#pragma unroll
    for (int i = 0; i < 16; i++) all &= pw[2 * i];
    if (wg == 0 && lane == 0 && all != 0xffffffffu) mbar_arrive(bars + 8 * MB_CLOSE);
  }
  mbar_wait(bars + 8 * (wg ? MB_GDONE + 1 : MB_CLOSE), 0);
  const uint32_t stg0 = sb + OFF_STG0, stg1 = sb + OFF_X + 32768;
  uint32_t sl = (wg ? stg1 : stg0) + w * 3072 + lane * 16;
#pragma unroll
  for (int mt = 0; mt < 2; mt++)
#pragma unroll
    for (int h = 0; h < 2; h++) {
      const float* a = acc[mt] + 32 + 8 * h;
      stsm4(sl + mt * 12288 + 2048 + h * 512, pack_bf(a[0], a[1]), pack_bf(a[2], a[3]), pack_bf(a[4], a[5]), pack_bf(a[6], a[7]));
    }
#pragma unroll 1
  for (int u = 0; u < 4; u++) {
#pragma unroll
    for (int i = 0; i < 16; i++) eq[i] = eq[16 + i];
    dual_softmax(pw, eq + 16);
    dual_softmax(pw + 4, eq + 24);
    if (u < 2) {
#pragma unroll
      for (int i = 0; i < 4; i++) stsm4(sl + i * 512, eq[16 + 4 * i], eq[17 + 4 * i], eq[18 + 4 * i], eq[19 + 4 * i]);
      if (wg) nb_arrive(NB_ST0 + u, 256);
      sl += 12288;
    }
#pragma unroll
    for (int i = 0; i < 24; i++) pw[i] = pw[i + 8];
  }
  TS(wg * 16 + 4);
  const uint32_t kvs = stg0;
  if (wg == 0) {
    nb_sync(NB_WG0, 128);
    mbar_wait(bars + 8 * MB_UFULL, 0);
    mbar_wait(bars + 8 * (MB_GDONE + 1), 0);
    float kv[12];
#pragma unroll
    for (int i = 0; i < 12; i++) kv[i] = 0.f;
    const int mi = lane >> 3;
    const uint32_t ao = w * 512 + (lane & 7) * 16 + ((mi & 1) * 2 + (mi >> 1)) * 128, bo = 2048 + (w >> 1) * 512 + lane * 16;
#pragma unroll 1
    for (int j = 0; j < 4; j++) {
      if (j >= 2) nb_sync(NB_ST0 + j - 2, 256);
      const uint32_t sg = (j >= 2 ? stg1 : stg0) + (j & 1) * 12288;
      uint32_t a[4][4], bb[4][4];
#pragma unroll
      for (int s = 0; s < 4; s++) { ldsm4t(a[s], sg + s * 3072 + ao); ldsm4t(bb[s], sg + s * 3072 + bo); }
#pragma unroll
      for (int s = 0; s < 4; s++) {
        mma(kv[0], kv[1], kv[2], kv[3], a[s][0], a[s][1], a[s][2], a[s][3], bb[s][0], bb[s][1]);
        mma(kv[4], kv[5], kv[6], kv[7], a[s][0], a[s][1], a[s][2], a[s][3], bb[s][2], bb[s][3]);
        mma(kv[8], kv[9], kv[10], kv[11], a[s][0], a[s][1], a[s][2], a[s][3], 0x3F803F80u, 0x3F803F80u);
      }
    }
    uint4* pp = g_part + (size_t)(hp * 8 + rt) * 272;
    st_x(pp + t, nz(fu(kv[0])), fu(kv[1]), fu(kv[2]), fu(kv[3]));
    st_x(pp + 128 + t, nz(fu(kv[4])), fu(kv[5]), fu(kv[6]), fu(kv[7]));
    if (c < 2) st_x32((uint32_t*)(pp + 256) + w * 16 + c * 8 + g, nz(fu(c ? kv[10] : kv[8])));
    TS(5);
    const uint4* ps = g_part + (size_t)hp * 8 * 272 + t;
    const uint32_t* zs = (const uint32_t*)(g_part + (size_t)(hp * 8 + (lane >> 4) * 4) * 272 + 256) + w * 16 + (lane & 15);
    uint4 v[16];
    uint32_t zv[4];
#pragma unroll 1
    for (int it = 0; it < SPIN_MAX; it++) {
#pragma unroll
      for (int i = 0; i < 16; i++) v[i] = ld_x(ps + (i >> 1) * 272 + (i & 1) * 128);
#pragma unroll
      for (int i = 0; i < 4; i++) zv[i] = ld_x32(zs + i * 1088);
      uint32_t m = min(min(zv[0], zv[1]), min(zv[2], zv[3]));
#pragma unroll
      for (int i = 0; i < 16; i++) m = min(m, v[i].x);
      if (__all_sync(0xffffffffu, m != 0)) break;
    }
    float s[8] = {uf(v[0].x), uf(v[0].y), uf(v[0].z), uf(v[0].w), uf(v[1].x), uf(v[1].y), uf(v[1].z), uf(v[1].w)};
#pragma unroll
    for (int r = 1; r < 8; r++) {
      s[0] += uf(v[2 * r].x); s[1] += uf(v[2 * r].y); s[2] += uf(v[2 * r].z); s[3] += uf(v[2 * r].w);
      s[4] += uf(v[2 * r + 1].x); s[5] += uf(v[2 * r + 1].y); s[6] += uf(v[2 * r + 1].z); s[7] += uf(v[2 * r + 1].w);
    }
    float zsum = (uf(zv[0]) + uf(zv[1])) + (uf(zv[2]) + uf(zv[3]));
    zsum += __shfl_xor_sync(0xffffffffu, zsum, 16);
    stsm4(kvs + w * 512 + lane * 16, pack_bf(s[0], s[1]), pack_bf(s[2], s[3]), pack_bf(s[4], s[5]), pack_bf(s[6], s[7]));
    if (lane < 16) sts16(kvs + 2048 + (w * 16 + lane) * 2, pack_bf(zsum, 0.f));
    TS(6);
  }
  nb_sync(NB_KV, 256);
  {
    uint32_t kb_[4][4], zb[8];
#pragma unroll
    for (int i = 0; i < 4; i++) ldsm4t(kb_[i], kvs + i * 512 + lane * 16);
#pragma unroll
    for (int i = 0; i < 8; i++) zb[i] = lds32(kvs + 2048 + i * 16 + c * 4);
    uint4* od = g_o + (size_t)((rt * 4 + wg * 2) * 32 + hp * 2) * 128 + t;
#pragma unroll 1
    for (int mt = 0; mt < 2; mt++) {
#pragma unroll
      for (int h = 0; h < 2; h++) {
        const uint32_t* e = eq + 8 * h;
        float n[8], dn[4];
        mma0(dn[0], dn[1], dn[2], dn[3], e[0], e[1], e[2], e[3], zb[4 * h], zb[4 * h + 1]);
        mma0(n[0], n[1], n[2], n[3], e[0], e[1], e[2], e[3], kb_[2 * h][0], kb_[2 * h][1]);
        mma0(n[4], n[5], n[6], n[7], e[0], e[1], e[2], e[3], kb_[2 * h][2], kb_[2 * h][3]);
        mma(dn[0], dn[1], dn[2], dn[3], e[4], e[5], e[6], e[7], zb[4 * h + 2], zb[4 * h + 3]);
        mma(n[0], n[1], n[2], n[3], e[4], e[5], e[6], e[7], kb_[2 * h + 1][0], kb_[2 * h + 1][1]);
        mma(n[4], n[5], n[6], n[7], e[4], e[5], e[6], e[7], kb_[2 * h + 1][2], kb_[2 * h + 1][3]);
        const float r0 = rcp(dn[0] + 1e-6f), r1 = rcp(dn[2] + 1e-6f);
        st_x(od + h * 128, nz(pack_bf(n[0] * r0, n[1] * r0)), pack_bf(n[2] * r1, n[3] * r1), pack_bf(n[4] * r0, n[5] * r0),
             pack_bf(n[6] * r1, n[7] * r1));
      }
#pragma unroll
      for (int i = 0; i < 16; i++) eq[i] = eq[16 + i];
      od += 4096;
    }
  }
  TS(wg * 16 + 7);
  const int rb = rt * 4 + (hp >> 2);
  const uint4* osrc = g_o + (size_t)(rb * 32 + wg * 16) * 128 + t;
  uint4 af[16];
#pragma unroll 1
  for (int it = 0; it < SPIN_MAX; it++) {
    uint32_t m = 0xffffffffu;
#pragma unroll
    for (int i = 0; i < 16; i++) af[i] = ld_x(osrc + i * 128);
#pragma unroll
    for (int i = 0; i < 16; i++) m = min(m, af[i].x);
    if (__all_sync(0xffffffffu, m != 0)) break;
  }
  TS(wg * 16 + 8);
#pragma unroll 1
  for (int j = 0; j < 5; j++) mbar_wait(bars + 8 * (j < 4 ? MB_WOFULL + wg * 4 + j : MB_BDONE), 0);
  TS(wg * 16 + 9);
  float oc[64];
  {
    const uint64_t db = mkdesc(sb + wo_addr(wg * 4), 8192, 1024, 1);
    WG_FENCE();
#pragma unroll
    for (int k = 0; k < 16; k++) wgmma_rs_n128(oc, af[k], db + 128 * (k & 3) + 1024 * (k >> 2), k);
    WG_COMMIT();
    WG_WAIT(0);
  }
  TS(wg * 16 + 10);
  const uint32_t xo = stg1 + wg * 16384 + t * 16, xi = stg1 + (wg ^ 1) * 16384 + t * 16;
#pragma unroll
  for (int i = 0; i < 8; i++) sts128(xo + i * 2048, fu(oc[32 + 4 * i]), fu(oc[33 + 4 * i]), fu(oc[34 + 4 * i]), fu(oc[35 + 4 * i]));
  nb_sync(NB_RED, 256);
  __nv_bfloat16* dst = P.out + (size_t)(rb * 64 + w * 16 + g) * 1024 + (hp & 3) * 128 + wg * 64 + 2 * c;
#pragma unroll
  for (int i = 0; i < 8; i++) {
    const uint4 v = lds128(xi + i * 2048);
    *(uint32_t*)(dst + i * 8) = pack_bf(oc[4 * i] + uf(v.x), oc[4 * i + 1] + uf(v.y));
    *(uint32_t*)(dst + i * 8 + 8192) = pack_bf(oc[4 * i + 2] + uf(v.z), oc[4 * i + 3] + uf(v.w));
  }
  TS(wg * 16 + 11);
}

typedef CUresult (*EncodeFn)(CUtensorMap*, CUtensorMapDataType, cuuint32_t, void*, const cuuint64_t*, const cuuint64_t*,
                             const cuuint32_t*, const cuuint32_t*, CUtensorMapInterleave, CUtensorMapSwizzle,
                             CUtensorMapL2promotion, CUtensorMapFloatOOBfill);

}

extern "C" void kernel_launch(void* const* d_in, const int* in_sizes, int n_in, void* d_out, int out_size) {
  (void)in_sizes; (void)n_in; (void)out_size;
  void* fn = nullptr;
  cudaDriverEntryPointQueryResult qr;
  cudaGetDriverEntryPoint("cuTensorMapEncodeTiled", &fn, cudaEnableDefault, &qr);
  EncodeFn enc = (EncodeFn)fn;
  CUtensorMap mx, mw, mo;
  const cuuint32_t es[3] = {1, 1, 1};
  {
    cuuint64_t dims[2] = {512, 2048}, st[1] = {1024};
    cuuint32_t box[2] = {64, 128};
    enc(&mx, CU_TENSOR_MAP_DATA_TYPE_BFLOAT16, 2, d_in[0], dims, st, box, es, CU_TENSOR_MAP_INTERLEAVE_NONE,
        CU_TENSOR_MAP_SWIZZLE_128B, CU_TENSOR_MAP_L2_PROMOTION_L2_128B, CU_TENSOR_MAP_FLOAT_OOB_FILL_NONE);
  }
  {
    cuuint64_t dims[3] = {512, 512, 3}, st[2] = {3072, 1024};
    cuuint32_t box[3] = {32, 64, 3};
    enc(&mw, CU_TENSOR_MAP_DATA_TYPE_BFLOAT16, 3, d_in[1], dims, st, box, es, CU_TENSOR_MAP_INTERLEAVE_NONE,
        CU_TENSOR_MAP_SWIZZLE_64B, CU_TENSOR_MAP_L2_PROMOTION_L2_128B, CU_TENSOR_MAP_FLOAT_OOB_FILL_NONE);
  }
  {
    cuuint64_t dims[2] = {512, 512}, st[1] = {1024};
    cuuint32_t box[2] = {64, 64};
    enc(&mo, CU_TENSOR_MAP_DATA_TYPE_BFLOAT16, 2, d_in[3], dims, st, box, es, CU_TENSOR_MAP_INTERLEAVE_NONE,
        CU_TENSOR_MAP_SWIZZLE_128B, CU_TENSOR_MAP_L2_PROMOTION_L2_128B, CU_TENSOR_MAP_FLOAT_OOB_FILL_NONE);
  }
  Params P;
  P.x = (const __nv_bfloat16*)d_in[0];
  P.wphi = (const __nv_bfloat16*)d_in[2];
  P.wo = (const __nv_bfloat16*)d_in[3];
  P.u = (const __nv_bfloat16*)d_in[4];
  P.logA = (const __nv_bfloat16*)d_in[5];
  P.Aim = (const __nv_bfloat16*)d_in[6];
  P.Cre = (const __nv_bfloat16*)d_in[7];
  P.Cim = (const __nv_bfloat16*)d_in[8];
  P.logdt = (const __nv_bfloat16*)d_in[9];
  P.Dskip = (const __nv_bfloat16*)d_in[10];
  P.out = (__nv_bfloat16*)d_out;
  cudaFuncSetAttribute(fused_kernel, cudaFuncAttributeMaxDynamicSharedMemorySize, SMEM_BYTES);
  fused_kernel<<<NCTA, NTHREADS, SMEM_BYTES>>>(mx, mw, mo, P);
}
```

```cpp
#include <cuda_runtime.h>
#include <cuda_bf16.h>
#include <cuda_fp16.h>
#include <cuda.h>
#include <stdint.h>

#define DBG_TS 0

namespace {

constexpr int NTHREADS = 512;
constexpr int NCTA = 128;
constexpr int OFF_W = 0;
constexpr int OFF_X = 98304;
constexpr int OFF_STG0 = 163840;
constexpr int OFF_U = 188416;
constexpr int U_CH = 4416, U_ODD = 2240, U_PAD = 128;
constexpr int OFF_T = OFF_U + 4 * U_CH;
constexpr int T_CH = 5216;
constexpr int T_D = 0;
constexpr int T_5 = 2144;
constexpr int T_3 = T_5 + 384;
constexpr int T_7 = T_5 + 1024;
constexpr int T_9 = T_7 + 320;
constexpr int T_KC = T_9 + 320;
constexpr int T_ST = T_5 - 1024;
constexpr int OFF_BAR = OFF_T + 4 * T_CH;
constexpr int SMEM_BYTES = OFF_BAR + 256 + 1024;
static_assert(T_KC + 2 * 656 <= T_CH, "table size");
static_assert(SMEM_BYTES <= 232448, "smem");
constexpr int MB_WFULL = 0, MB_XFULL = 8, MB_WOFULL = 12, MB_UFULL = 20, MB_URAW = 21, MB_XEMPTY = 22,
              MB_GDONE = 26  , MB_BDONE = 28, MB_CLOSE = 29;
constexpr int NB_WG0 = 1, NB_KPART = 2, NB_ST0 = 3  , NB_KV = 5, NB_RED = 6, NB_INIT = 7, NB_PREP = 8, NB_PROD = 9;
constexpr int STEP_PF = 0, STEP_U = 2;
constexpr int T_PA = 2144, T_PB = 4192;
constexpr int SPIN_MAX = 1 << 18;

__device__ unsigned g_cnt;
__device__ uint4 g_uT[512 * 256];
__device__ uint4 g_part[16 * 8 * 144];
__device__ uint4 g_o[32 * 32 * 128];
__device__ uint4 g_y[512 * 8 * 32];
#define TS(i) do {} while (0)
#define TS1(i) do {} while (0)

__device__ __forceinline__ uint32_t smem_u32(const void* p) { return (uint32_t)__cvta_generic_to_shared(p); }
__device__ __forceinline__ void mbar_arrive(uint32_t b) {
  asm volatile("mbarrier.arrive.shared::cta.b64 _, [%0];" ::"r"(b) : "memory");
}
__device__ __forceinline__ void mbar_wait(uint32_t b, uint32_t parity) {
  uint32_t done = 0;
#pragma unroll 1
  for (int i = 0; i < SPIN_MAX && !done; i++) {
    asm volatile("{\n.reg .pred p;\nmbarrier.try_wait.parity.shared::cta.b64 p, [%1], %2;\nselp.u32 %0, 1, 0, p;\n}\n"
                 : "=r"(done) : "r"(b), "r"(parity) : "memory");
  }
}
__device__ __forceinline__ void nb_sync(int id, int n) { asm volatile("bar.sync %0, %1;" ::"r"(id), "r"(n) : "memory"); }
__device__ __forceinline__ void nb_arrive(int id, int n) { asm volatile("bar.arrive %0, %1;" ::"r"(id), "r"(n) : "memory"); }
#define ELECT "{\n.reg .pred p;\nelect.sync _|p, 0xffffffff;\n@p "
__device__ __forceinline__ void e_init(uint32_t b, int n) {
  asm volatile(ELECT "mbarrier.init.shared::cta.b64 [%0], %1;\n}\n" ::"r"(b), "r"(n) : "memory");
}
__device__ __forceinline__ void e_expect(uint32_t b, int bytes) {
  asm volatile(ELECT "mbarrier.arrive.expect_tx.shared::cta.b64 _, [%0], %1;\n}\n" ::"r"(b), "r"(bytes) : "memory");
}
__device__ __forceinline__ void e_tma2d(uint32_t dst, const CUtensorMap* m, uint32_t bar, int c0, int c1) {
  asm volatile(ELECT "cp.async.bulk.tensor.2d.shared::cluster.global.mbarrier::complete_tx::bytes [%0], [%1, {%3,%4}], [%2];\n}\n"
               ::"r"(dst), "l"(m), "r"(bar), "r"(c0), "r"(c1) : "memory");
}
__device__ __forceinline__ void e_tma3d(uint32_t dst, const CUtensorMap* m, uint32_t bar, int c0, int c1, int c2) {
  asm volatile(ELECT "cp.async.bulk.tensor.3d.shared::cluster.global.mbarrier::complete_tx::bytes [%0], [%1, {%3,%4,%5}], [%2];\n}\n"
               ::"r"(dst), "l"(m), "r"(bar), "r"(c0), "r"(c1), "r"(c2) : "memory");
}
__device__ __forceinline__ void e_tma5d(uint32_t dst, const CUtensorMap* m, uint32_t bar, int c0, int c4) {
  asm volatile(ELECT "cp.async.bulk.tensor.5d.shared::cluster.global.mbarrier::complete_tx::bytes [%0], [%1, {%3,%5,%5,%5,%4}], [%2];\n}\n"
               ::"r"(dst), "l"(m), "r"(bar), "r"(c0), "r"(c4), "r"(0) : "memory");
}
__device__ __forceinline__ void e_bulk(uint32_t dst, const void* src, int bytes, uint32_t bar) {
  asm volatile(ELECT "cp.async.bulk.shared::cluster.global.mbarrier::complete_tx::bytes [%0], [%1], %2, [%3];\n}\n"
               ::"r"(dst), "l"(src), "r"(bytes), "r"(bar) : "memory");
}
__device__ __forceinline__ void e_prefetch(const void* p, int bytes) {
  asm volatile(ELECT "cp.async.bulk.prefetch.L2.global [%0], %1;\n}\n" ::"l"(p), "r"(bytes) : "memory");
}
__device__ __forceinline__ void e_store2d(const CUtensorMap* m, uint32_t src, int c0, int c1) {
  asm volatile(ELECT "cp.async.bulk.tensor.2d.global.shared::cta.bulk_group [%0, {%2,%3}], [%1];\n"
               "@p cp.async.bulk.commit_group;\n@p cp.async.bulk.wait_group.read 0;\n}\n"
               ::"l"(m), "r"(src), "r"(c0), "r"(c1) : "memory");
}
__device__ __forceinline__ uint64_t mkdesc(uint32_t addr, uint32_t lbo, uint32_t sbo, int swz) {
  return (uint64_t)((addr & 0x3FFFF) >> 4) | ((uint64_t)(lbo >> 4) << 16) | ((uint64_t)(sbo >> 4) << 32) |
         ((uint64_t)swz << 62);
}
#define WG_FENCE() asm volatile("wgmma.fence.sync.aligned;" ::: "memory")
#define WG_COMMIT() asm volatile("wgmma.commit_group.sync.aligned;" ::: "memory")
#define WG_WAIT(n) asm volatile("wgmma.wait_group.sync.aligned " #n ";" ::: "memory")

__device__ __forceinline__ void mma(float& d0, float& d1, float& d2, float& d3, uint32_t a0, uint32_t a1, uint32_t a2,
                                    uint32_t a3, uint32_t b0, uint32_t b1) {
  asm volatile("mma.sync.aligned.m16n8k16.row.col.f32.bf16.bf16.f32 {%0,%1,%2,%3},{%4,%5,%6,%7},{%8,%9},{%0,%1,%2,%3};"
               : "+f"(d0), "+f"(d1), "+f"(d2), "+f"(d3)
               : "r"(a0), "r"(a1), "r"(a2), "r"(a3), "r"(b0), "r"(b1));
}
__device__ __forceinline__ void mmac(float (&d)[4], uint32_t a0, uint32_t a1, uint32_t a2, uint32_t a3, uint32_t b0,
                                     uint32_t b1, const float (&c)[4]) {
  asm volatile("mma.sync.aligned.m16n8k16.row.col.f32.bf16.bf16.f32 {%0,%1,%2,%3},{%4,%5,%6,%7},{%8,%9},{%10,%11,%12,%13};"
               : "=f"(d[0]), "=f"(d[1]), "=f"(d[2]), "=f"(d[3])
               : "r"(a0), "r"(a1), "r"(a2), "r"(a3), "r"(b0), "r"(b1), "f"(c[0]), "f"(c[1]), "f"(c[2]), "f"(c[3]));
}
__device__ __forceinline__ void mma_p(int p, float (&d)[4], uint32_t a0, uint32_t a1, uint32_t a2, uint32_t a3, uint32_t b0, uint32_t b1) {
  asm volatile("{\n.reg .pred q;\nsetp.ne.b32 q, %10, 0;\n"
               "@q mma.sync.aligned.m16n8k16.row.col.f32.bf16.bf16.f32 {%0,%1,%2,%3},{%4,%5,%6,%7},{%8,%9},{%0,%1,%2,%3};\n}\n"
               : "+f"(d[0]), "+f"(d[1]), "+f"(d[2]), "+f"(d[3])
               : "r"(a0), "r"(a1), "r"(a2), "r"(a3), "r"(b0), "r"(b1), "r"(p));
}
__device__ __forceinline__ void mmac_p(int p, float (&d)[4], uint32_t a0, uint32_t a1, uint32_t a2, uint32_t a3, uint32_t b0,
                                       uint32_t b1, const float (&c)[4]) {
  asm volatile("{\n.reg .pred q;\nsetp.ne.b32 q, %14, 0;\n"
               "@q mma.sync.aligned.m16n8k16.row.col.f32.bf16.bf16.f32 {%0,%1,%2,%3},{%4,%5,%6,%7},{%8,%9},{%10,%11,%12,%13};\n}\n"
               : "+f"(d[0]), "+f"(d[1]), "+f"(d[2]), "+f"(d[3])
               : "r"(a0), "r"(a1), "r"(a2), "r"(a3), "r"(b0), "r"(b1), "f"(c[0]), "f"(c[1]), "f"(c[2]), "f"(c[3]), "r"(p));
}
__device__ __forceinline__ void mma_k8(float (&d)[4], uint32_t a0, uint32_t a1, uint32_t b0) {
  asm volatile("mma.sync.aligned.m16n8k8.row.col.f32.bf16.bf16.f32 {%0,%1,%2,%3},{%4,%5},{%6},{%0,%1,%2,%3};"
               : "+f"(d[0]), "+f"(d[1]), "+f"(d[2]), "+f"(d[3]) : "r"(a0), "r"(a1), "r"(b0));
}
__device__ __forceinline__ void mma0(float& d0, float& d1, float& d2, float& d3, uint32_t a0, uint32_t a1, uint32_t a2,
                                     uint32_t a3, uint32_t b0, uint32_t b1) {
  asm volatile("mma.sync.aligned.m16n8k16.row.col.f32.bf16.bf16.f32 {%0,%1,%2,%3},{%4,%5,%6,%7},{%8,%9},{%10,%10,%10,%10};"
               : "=f"(d0), "=f"(d1), "=f"(d2), "=f"(d3)
               : "r"(a0), "r"(a1), "r"(a2), "r"(a3), "r"(b0), "r"(b1), "f"(0.f));
}
__device__ __forceinline__ uint32_t pack_bf(float lo, float hi) {
  uint32_t r;
  asm("cvt.rn.bf16x2.f32 %0, %1, %2;" : "=r"(r) : "f"(hi), "f"(lo));
  return r;
}
__device__ __forceinline__ float bf_lo(uint32_t w) { return __uint_as_float(w << 16); }
__device__ __forceinline__ float bf_hi(uint32_t w) { return __uint_as_float(w & 0xffff0000u); }
__device__ __forceinline__ float bf_round(float x) { return __bfloat162float(__float2bfloat16_rn(x)); }
__device__ __forceinline__ uint32_t bmax2(uint32_t a, uint32_t b) {
  uint32_t r; asm("max.bf16x2 %0, %1, %2;" : "=r"(r) : "r"(a), "r"(b)); return r;
}
__device__ __forceinline__ uint32_t bmin2(uint32_t a, uint32_t b) {
  uint32_t r; asm("min.bf16x2 %0, %1, %2;" : "=r"(r) : "r"(a), "r"(b)); return r;
}
__device__ __forceinline__ float ex2(float x) { float r; asm("ex2.approx.ftz.f32 %0, %1;" : "=f"(r) : "f"(x)); return r; }
__device__ __forceinline__ float rcp(float x) { float r; asm("rcp.approx.ftz.f32 %0, %1;" : "=f"(r) : "f"(x)); return r; }
__device__ __forceinline__ void ldsm4(uint32_t (&r)[4], uint32_t a) {
  asm volatile("ldmatrix.sync.aligned.m8n8.x4.shared.b16 {%0,%1,%2,%3}, [%4];"
               : "=r"(r[0]), "=r"(r[1]), "=r"(r[2]), "=r"(r[3]) : "r"(a) : "memory");
}
__device__ __forceinline__ void ldsm4t(uint32_t (&r)[4], uint32_t a) {
  asm volatile("ldmatrix.sync.aligned.m8n8.x4.trans.shared.b16 {%0,%1,%2,%3}, [%4];"
               : "=r"(r[0]), "=r"(r[1]), "=r"(r[2]), "=r"(r[3]) : "r"(a) : "memory");
}
__device__ __forceinline__ void stsm4(uint32_t a, uint32_t r0, uint32_t r1, uint32_t r2, uint32_t r3) {
  asm volatile("stmatrix.sync.aligned.m8n8.x4.shared.b16 [%0], {%1,%2,%3,%4};"
               ::"r"(a), "r"(r0), "r"(r1), "r"(r2), "r"(r3) : "memory");
}
__device__ __forceinline__ uint32_t lds32(uint32_t a) {
  uint32_t r; asm volatile("ld.shared.u32 %0, [%1];" : "=r"(r) : "r"(a) : "memory"); return r;
}
__device__ __forceinline__ uint32_t lds16(uint32_t a) {
  uint32_t r; asm volatile("{\n.reg .u16 h;\nld.shared.u16 h, [%1];\ncvt.u32.u16 %0, h;\n}\n" : "=r"(r) : "r"(a) : "memory"); return r;
}
__device__ __forceinline__ uint2 lds64(uint32_t a) {
  uint2 r; asm volatile("ld.shared.v2.u32 {%0,%1}, [%2];" : "=r"(r.x), "=r"(r.y) : "r"(a) : "memory"); return r;
}
__device__ __forceinline__ uint4 lds128(uint32_t a) {
  uint4 r;
  asm volatile("ld.shared.v4.u32 {%0,%1,%2,%3}, [%4];" : "=r"(r.x), "=r"(r.y), "=r"(r.z), "=r"(r.w) : "r"(a) : "memory");
  return r;
}
__device__ __forceinline__ void sts32(uint32_t a, uint32_t v) { asm volatile("st.shared.u32 [%0], %1;" ::"r"(a), "r"(v) : "memory"); }
__device__ __forceinline__ void sts16(uint32_t a, uint32_t v) {
  asm volatile("{\n.reg .u16 h;\ncvt.u16.u32 h, %1;\nst.shared.u16 [%0], h;\n}\n" ::"r"(a), "r"(v) : "memory");
}
__device__ __forceinline__ void sts64(uint32_t a, uint32_t x, uint32_t y) {
  asm volatile("st.shared.v2.u32 [%0], {%1,%2};" ::"r"(a), "r"(x), "r"(y) : "memory");
}
__device__ __forceinline__ void sts128(uint32_t a, uint32_t x, uint32_t y, uint32_t z, uint32_t w) {
  asm volatile("st.shared.v4.u32 [%0], {%1,%2,%3,%4};" ::"r"(a), "r"(x), "r"(y), "r"(z), "r"(w) : "memory");
}
__device__ __forceinline__ uint4 ld_x(const uint4* p) {
  uint4 r;
  asm volatile("{\n.reg .b128 t;\nld.relaxed.gpu.global.b128 t, [%4];\nmov.b128 {%0,%1,%2,%3}, t;\n}\n"
               : "=r"(r.x), "=r"(r.y), "=r"(r.z), "=r"(r.w) : "l"(p) : "memory");
  return r;
}
__device__ __forceinline__ uint32_t ld_x32(const uint32_t* p) {
  uint32_t r; asm volatile("ld.relaxed.gpu.global.u32 %0, [%1];" : "=r"(r) : "l"(p) : "memory"); return r;
}
__device__ __forceinline__ void st_x(uint4* p, uint32_t x, uint32_t y, uint32_t z, uint32_t w) {
  asm volatile("{\n.reg .b128 t;\nmov.b128 t, {%1,%2,%3,%4};\nst.relaxed.gpu.global.b128 [%0], t;\n}\n"
               ::"l"(p), "r"(x), "r"(y), "r"(z), "r"(w) : "memory");
}
__device__ __forceinline__ void st_x_p(int p, uint4* a, uint32_t x, uint32_t y, uint32_t z, uint32_t w) {
  asm volatile("{\n.reg .b128 t;\n.reg .pred q;\nsetp.ne.b32 q, %5, 0;\nmov.b128 t, {%1,%2,%3,%4};\n@q st.relaxed.gpu.global.b128 [%0], t;\n}\n"
               ::"l"(a), "r"(x), "r"(y), "r"(z), "r"(w), "r"(p) : "memory");
}
__device__ __forceinline__ void sts64_p(int p, uint32_t a, uint32_t x, uint32_t y) {
  asm volatile("{\n.reg .pred q;\nsetp.ne.b32 q, %3, 0;\n@q st.shared.v2.u32 [%0], {%1,%2};\n}\n" ::"r"(a), "r"(x), "r"(y), "r"(p) : "memory");
}
__device__ __forceinline__ void st_x32(uint32_t* p, uint32_t x) {
  asm volatile("st.relaxed.gpu.global.u32 [%0], %1;" ::"l"(p), "r"(x) : "memory");
}
__device__ __forceinline__ uint32_t nz(uint32_t w) { return max(w, 1u); }
__device__ __forceinline__ uint32_t fu(float x) { return __float_as_uint(x); }
__device__ __forceinline__ float uf(uint32_t x) { return __uint_as_float(x); }

__device__ __forceinline__ void wgmma_ss_n96(float (&d)[48], uint64_t da, uint64_t db, int sc) {
  asm volatile("{\n.reg .pred p;\nsetp.ne.b32 p, %50, 0;\n"
      "wgmma.mma_async.sync.aligned.m64n96k16.f32.bf16.bf16 "
      "{%0,%1,%2,%3,%4,%5,%6,%7,%8,%9,%10,%11,%12,%13,%14,%15,%16,%17,%18,%19,%20,%21,%22,%23,%24,%25,%26,%27,%28,%29,%30,%31,%32,%33,%34,%35,%36,%37,%38,%39,%40,%41,%42,%43,%44,%45,%46,%47}, "
      "%48, %49, p, 1, 1, 0, 1;\n}\n"
      : "+f"(d[0]), "+f"(d[1]), "+f"(d[2]), "+f"(d[3]), "+f"(d[4]), "+f"(d[5]), "+f"(d[6]), "+f"(d[7]),
        "+f"(d[8]), "+f"(d[9]), "+f"(d[10]), "+f"(d[11]), "+f"(d[12]), "+f"(d[13]), "+f"(d[14]), "+f"(d[15]),
        "+f"(d[16]), "+f"(d[17]), "+f"(d[18]), "+f"(d[19]), "+f"(d[20]), "+f"(d[21]), "+f"(d[22]), "+f"(d[23]),
        "+f"(d[24]), "+f"(d[25]), "+f"(d[26]), "+f"(d[27]), "+f"(d[28]), "+f"(d[29]), "+f"(d[30]), "+f"(d[31]),
        "+f"(d[32]), "+f"(d[33]), "+f"(d[34]), "+f"(d[35]), "+f"(d[36]), "+f"(d[37]), "+f"(d[38]), "+f"(d[39]),
        "+f"(d[40]), "+f"(d[41]), "+f"(d[42]), "+f"(d[43]), "+f"(d[44]), "+f"(d[45]), "+f"(d[46]), "+f"(d[47])
      : "l"(da), "l"(db), "r"(sc));
}

__device__ __forceinline__ void wgmma_rs_n128(float (&d)[64], const uint4& a, uint64_t db, int sc) {
  asm volatile("{\n.reg .pred p;\nsetp.ne.b32 p, %69, 0;\n"
      "wgmma.mma_async.sync.aligned.m64n128k16.f32.bf16.bf16 "
      "{%0,%1,%2,%3,%4,%5,%6,%7,%8,%9,%10,%11,%12,%13,%14,%15,%16,%17,%18,%19,%20,%21,%22,%23,%24,%25,%26,%27,%28,%29,%30,%31,%32,%33,%34,%35,%36,%37,%38,%39,%40,%41,%42,%43,%44,%45,%46,%47,%48,%49,%50,%51,%52,%53,%54,%55,%56,%57,%58,%59,%60,%61,%62,%63}, "
      "{%64,%65,%66,%67}, %68, p, 1, 1, 1;\n}\n"
      : "+f"(d[0]), "+f"(d[1]), "+f"(d[2]), "+f"(d[3]), "+f"(d[4]), "+f"(d[5]), "+f"(d[6]), "+f"(d[7]),
        "+f"(d[8]), "+f"(d[9]), "+f"(d[10]), "+f"(d[11]), "+f"(d[12]), "+f"(d[13]), "+f"(d[14]), "+f"(d[15]),
        "+f"(d[16]), "+f"(d[17]), "+f"(d[18]), "+f"(d[19]), "+f"(d[20]), "+f"(d[21]), "+f"(d[22]), "+f"(d[23]),
        "+f"(d[24]), "+f"(d[25]), "+f"(d[26]), "+f"(d[27]), "+f"(d[28]), "+f"(d[29]), "+f"(d[30]), "+f"(d[31]),
        "+f"(d[32]), "+f"(d[33]), "+f"(d[34]), "+f"(d[35]), "+f"(d[36]), "+f"(d[37]), "+f"(d[38]), "+f"(d[39]),
        "+f"(d[40]), "+f"(d[41]), "+f"(d[42]), "+f"(d[43]), "+f"(d[44]), "+f"(d[45]), "+f"(d[46]), "+f"(d[47]),
        "+f"(d[48]), "+f"(d[49]), "+f"(d[50]), "+f"(d[51]), "+f"(d[52]), "+f"(d[53]), "+f"(d[54]), "+f"(d[55]),
        "+f"(d[56]), "+f"(d[57]), "+f"(d[58]), "+f"(d[59]), "+f"(d[60]), "+f"(d[61]), "+f"(d[62]), "+f"(d[63])
      : "r"(a.x), "r"(a.y), "r"(a.z), "r"(a.w), "l"(db), "r"(sc));
}

struct Params {
  const __nv_bfloat16 *x, *wphi, *wo, *u, *logA, *Aim, *Cre, *Cim, *logdt, *Dskip;
  __nv_bfloat16* out;
};

__device__ __forceinline__ uint4 tr_row(const uint4 (&v)[8], int i) {
  uint32_t o[4];
#pragma unroll
  for (int m = 0; m < 4; m++) {
    const uint4 &ra = v[2 * m], &rb = v[2 * m + 1];
    const int k = i >> 1;
    const uint32_t xa = k == 0 ? ra.x : k == 1 ? ra.y : k == 2 ? ra.z : ra.w;
    const uint32_t xb = k == 0 ? rb.x : k == 1 ? rb.y : k == 2 ? rb.z : rb.w;
    o[m] = __byte_perm(xa, xb, (i & 1) ? 0x7632 : 0x5410);
  }
  return make_uint4(o[0], o[1], o[2], o[3]);
}

struct cpx { float r, i; };
__device__ __forceinline__ cpx cmul(cpx a, cpx b) { return {a.r * b.r - a.i * b.i, a.r * b.i + a.i * b.r}; }
__device__ __forceinline__ cpx csq(cpx a) { return {a.r * a.r - a.i * a.i, 2.f * (a.r * a.i)}; }
__device__ __forceinline__ cpx polar(float e, float t) {
  const float m = ex2(e);
  return {m * __cosf(t), m * __sinf(t)};
}
__device__ __forceinline__ float frac(float t) { return t - rintf(t); }

struct KgenRaw { uint32_t la, ai, cr, ci; unsigned short ldt; };
__device__ __forceinline__ void kgen_prep(KgenRaw r, int half, int lane, uint32_t tb, float& dt, float& k2048) {
  const float TWO_PI = 6.283185307179586f;
  dt = bf_round(expf(bf_lo(r.ldt)));
  float ks = 0.f;
  int m = half * 64 + 2 * lane;
#pragma unroll 1
  for (int j = 0; j < 2; j++, m++) {
    const float a2 = -(bf_round(expf(bf_lo(r.la))) * dt) * 1.4426950408889634f;
    const float f = frac((bf_lo(r.ai) * dt) * 0.15915494309189535f);
    const cpx w64 = polar(a2 * 64.f, frac(f * 64.f) * TWO_PI);
    const cpx we = polar(a2 * 2048.f, frac(f * 2048.f) * TWO_PI);
    ks += bf_lo(r.cr) * we.r - bf_lo(r.ci) * we.i;
    sts128(tb + T_PA + m * 16, fu(a2), fu(f * TWO_PI), fu(w64.r), fu(w64.i));
    sts64(tb + T_PB + m * 8, __byte_perm(r.cr, r.ci, 0x5410), fu(frac(f * 128.f) * TWO_PI));
    r.la >>= 16; r.ai >>= 16; r.cr >>= 16; r.ci >>= 16;
  }
#pragma unroll
  for (int o2 = 16; o2; o2 >>= 1) ks += __shfl_xor_sync(0xffffffffu, ks, o2);
  k2048 = ks;
}
__device__ __forceinline__ void kgen_round(int s0, int cnt, int lane, uint32_t tb, uint32_t open_bar, float (&k)[5][4]) {
  const int g = lane >> 2, c = lane & 3;
  const float pg = (float)g;
  const float n2 = (float)(2 + (g & 1)), m2 = (float)(g & 6), p2 = 128.f * n2 + m2;
  const float n3 = (float)(4 + (g & 3)), m3 = (float)(g & 4), p3 = 128.f * n3 + m3;
  uint32_t pa = tb + T_PA + (8 * s0 + c) * 16, pb = tb + T_PB + (8 * s0 + c) * 8;
  uint4 qn[2] = {lds128(pa), lds128(pa + 64)};
  uint2 cn[2] = {lds64(pb), lds64(pb + 32)};
  uint32_t Q[6][14];
#pragma unroll 1
  for (int s = 0; s < cnt; s++) {
    const uint4 qq[2] = {qn[0], qn[1]};
    const uint2 cc[2] = {cn[0], cn[1]};
    pa += 128; pb += 64;
    qn[0] = lds128(pa); qn[1] = lds128(pa + 64);
    cn[0] = lds64(pb); cn[1] = lds64(pb + 32);
    uint32_t o[14];
#pragma unroll
    for (int h = 0; h < 2; h++) {
      const float a2 = uf(qq[h].x), f = uf(qq[h].y), f128 = uf(cc[h].y);
      const cpx w64 = {uf(qq[h].z), uf(qq[h].w)};
      const cpx C = {bf_lo(cc[h].x), bf_hi(cc[h].x)};
      const cpx d1 = polar(a2 * pg, f * pg);
      const cpx t2 = polar(a2 * p2, fmaf(f128, n2, f * m2));
      const cpx t3 = polar(a2 * p3, fmaf(f128, n3, f * m3));
      const cpx s8 = csq(csq(csq(d1)));
      const cpx z = cmul(s8, w64);
      const cpx a0 = cmul(C, s8), a1 = cmul(C, z);
      const cpx t1 = cmul(d1, csq(w64));
      const cpx t4 = csq(csq(csq(csq(z))));
      o[2 * h] = pack_bf(a0.r, -a0.i);
      o[2 * h + 1] = pack_bf(a1.r, -a1.i);
      o[4 + h] = pack_bf(d1.r, d1.i);
      o[6 + h] = pack_bf(t1.r, t1.i);
      o[8 + h] = pack_bf(t2.r, t2.i);
      o[10 + h] = pack_bf(t3.r, t3.i);
      o[12 + h] = pack_bf(t4.r, t4.i);
    }
#define KQ(i) case i: _Pragma("unroll") for (int e = 0; e < 14; e++) asm volatile("mov.b32 %0, %1;" : "=r"(Q[i][e]) : "r"(o[e])); break;
    switch (s) { KQ(0) KQ(1) KQ(2) KQ(3) KQ(4) default: KQ(5) }
#undef KQ
  }
  TS(40 + (s0 >> 2));
  mbar_wait(open_bar, 0);
#pragma unroll
  for (int s = 0; s < 6; s++)
#pragma unroll
    for (int j = 0; j < 5; j++) mma_p(s < 4 || cnt > 4, k[j], Q[s][0], Q[s][1], Q[s][2], Q[s][3], Q[s][4 + 2 * j], Q[s][5 + 2 * j]);
}

__device__ __forceinline__ void build_tables(uint32_t tb, int lane, float (&k)[5][4], float k2048) {
  const int g = lane >> 2, c = lane & 3;
  const uint32_t kc = tb + T_KC + 16;
  {
    const uint32_t a0 = kc + 16 * g + 4 * c, a2 = kc + 2 * (256 + 4 * g + c);
    const uint32_t a3 = kc + 2 * (384 + 2 * g + 64 * (c & 1) + (c >> 1)), a4 = kc + 2 * (512 + g + 32 * c);
#pragma unroll
    for (int r = 0; r < 2; r++) {
      sts32(a0 + 128 * r, pack_bf(k[0][2 * r], k[0][2 * r + 1]));
      sts32(a0 + 128 * r + 256, pack_bf(k[1][2 * r], k[1][2 * r + 1]));
      const uint32_t w2 = pack_bf(k[2][2 * r], k[2][2 * r + 1]);
      const uint32_t w3 = pack_bf(k[3][2 * r], k[3][2 * r + 1]);
      const uint32_t w4 = pack_bf(k[4][2 * r], k[4][2 * r + 1]);
      sts16(a2 + 64 * r, w2); sts16(a2 + 64 * r + 128, w2 >> 16);
      sts16(a3 + 32 * r, w3); sts16(a3 + 32 * r + 64, w3 >> 16);
      sts16(a4 + 16 * r, w4); sts16(a4 + 16 * r + 32, w4 >> 16);
    }
  }
  if (lane == 0) { sts16(kc + 2 * 640, pack_bf(k2048, 0.f)); sts16(kc - 2, 0); }
  __syncwarp();
  const uint32_t td = tb + T_D + 32;
  {
    const uint4 v = lds128(kc + 16 * lane);
    const uint32_t pv = lds16(kc + 16 * lane - 2);
    sts128(td + 32 * lane, __byte_perm(v.x, pv, 0x5410), __byte_perm(v.x, v.x, 0x1032), __byte_perm(v.y, v.x, 0x7610),
           __byte_perm(v.y, v.y, 0x1032));
    sts128(td + 32 * lane + 16, __byte_perm(v.z, v.y, 0x7610), __byte_perm(v.z, v.z, 0x1032),
           __byte_perm(v.w, v.z, 0x7610), __byte_perm(v.w, v.w, 0x1032));
  }
  {
    const uint2 v = lds64(kc + 512 + 8 * lane);
    const uint32_t k4 = lds16(kc + 512 + 8 * lane + 8);
    const uint32_t pv = lds16(kc + (lane == 0 ? 510 : 512 + 8 * lane));
    const uint32_t k22 = __byte_perm(v.y, v.y, 0x1010);
    sts128(td + 1024 + 32 * lane, __byte_perm(v.x, pv, 0x5410), __byte_perm(v.x, v.x, 0x1010),
           __byte_perm(v.x, v.x, 0x1032), __byte_perm(v.y, v.x, 0x7610));
    sts128(td + 1024 + 32 * lane + 16, k22, k22, __byte_perm(v.y, v.y, 0x1032), __byte_perm(k4, v.y, 0x7610));
  }
  {
    const uint32_t kk = lds16(kc + 2 * 384);
    const uint32_t w = lane < 3 ? (kk | (kk << 16)) : (lane == 3 ? (kk << 16) : 0u);
    if (lane < 24) sts32(td + 4 * (lane < 16 ? 512 + lane : lane - 24), w);
    const uint32_t lo_ = lds16(kc + 2 * 511), le_ = lds16(kc + 2 * 512);
    const uint32_t ja = tb + T_5 + (lane < 16 ? 4 * lane : 256 + 4 * lane);
    sts32(ja, lane == 16 ? (le_ << 16) : 0u);
    sts32(ja + 384, lane == 16 ? (lo_ << 16) : 0u);
    sts32(tb + (lane < 16 ? T_7 : T_9 - 64) + 4 * lane, 0u);
  }
#pragma unroll
  for (int s = 0; s < 2; s++) {
    const uint32_t b = kc + 2 * (s ? 512 : 384) + 8 * lane;
    const uint2 v = lds64(b);
    uint32_t em = lds16(b - 2), e0 = v.x;
    const uint32_t e4 = lds16(b + 8);
    if (lane == 0) { em = 0; e0 = 0; }
    sts64(tb + (s ? T_7 : T_3) + 64 + 8 * lane, __byte_perm(v.x, em, 0x5432), __byte_perm(v.y, v.x, 0x7632));
    sts64(tb + (s ? T_9 : T_5) + 64 + 8 * lane, __byte_perm(v.y, e0, 0x5410), __byte_perm(e4, v.y, 0x5410));
  }
  __syncwarp();
}

__device__ __forceinline__ uint32_t box2w(int lo, int n, int o) {
  return ((unsigned)(o - lo) < (unsigned)n ? 0x3F80u : 0u) | ((unsigned)(o + 1 - lo) < (unsigned)n ? 0x3F800000u : 0u);
}

__device__ __forceinline__ void conv_channel(uint32_t ub, uint32_t tb, int lane, uint4* ydst) {
  const int g = lane >> 2, c = lane & 3, x = g - 2 * c;
  const uint32_t st = tb + T_ST + lane * 8;
  const int mi = lane >> 3;
  const uint32_t qa = ub + U_PAD + 16 * (lane & 7) + ((mi == 0 || mi == 3) ? U_ODD : 0) - (mi == 0 ? 16 : 0);
  const uint32_t kv = lds16(tb + T_KC + 16 + 2 * 512);
  {
    const uint32_t hb = ub + U_PAD + (mi & 1) * U_ODD + 16 * ((lane >> 4) + (lane & 7)) - 16;
    const int oh = c < 2 ? 8 + 2 * c : 2 * c - 8;
    const uint32_t bx0 = box2w(g - 4, 9, 2 * c), bx1 = box2w(g - 3, 7, 2 * c), bx2 = box2w(g - 4, 9, oh), bx3 = box2w(g - 3, 7, oh);
    uint32_t f7[9], f9a[9], f9b[9];
    const uint32_t fa = tb + T_7 + 4 * (8 + x);
#pragma unroll
    for (int m = 0; m < 9; m++) {
      f7[m] = lds32(fa + 32 * m);
      f9b[m] = lds32(fa + 320 + 32 * m);
      f9a[m] = lds32(fa + 316 + 32 * m);
    }
    TS(36);
    uint32_t z09[8], z07[8], zm9[8], zm7[8];
#pragma unroll
    for (int i = 0; i < 8; i++) {
      uint32_t h[4];
      ldsm4(h, hb + 128 * i);
      float y0, y1, y2, y3, w0, w1, w2, w3;
      mma0(y0, y1, y2, y3, bx0, bx1, bx2, bx3, h[2], c < 2 ? h[3] : h[1]);
      mma0(w0, w1, w2, w3, bx0, bx1, bx2, bx3, h[1], c < 2 ? h[2] : h[0]);
      z09[i] = pack_bf(y0, y1); z07[i] = pack_bf(y2, y3);
      zm9[i] = pack_bf(w0, w1); zm7[i] = pack_bf(w2, w3);
    }
    float a[4][2][4];
#pragma unroll
    for (int kap = 0; kap < 4; kap++)
#pragma unroll
      for (int sg = 0; sg < 2; sg++)
#pragma unroll
        for (int bk = 3; bk >= kap; bk--) {
          const int m = 2 * (bk - kap) + 1;
          float(&a0)[4] = a[bk][0];
          float(&a1)[4] = a[bk][1];
          if (sg == 0 && kap == 0) {
            mma0(a0[0], a0[1], a0[2], a0[3], f9a[m], f9a[m + 1], f9a[m - 1], f9a[m], z09[0], z09[1]);
            mma0(a1[0], a1[1], a1[2], a1[3], f9b[m], f9b[m + 1], f9b[m - 1], f9b[m], zm9[0], zm9[1]);
          } else if (sg == 0) {
            mma(a0[0], a0[1], a0[2], a0[3], f9a[m], f9a[m + 1], f9a[m - 1], f9a[m], z09[2 * kap], z09[2 * kap + 1]);
            mma(a1[0], a1[1], a1[2], a1[3], f9b[m], f9b[m + 1], f9b[m - 1], f9b[m], zm9[2 * kap], zm9[2 * kap + 1]);
          } else {
            mma(a0[0], a0[1], a0[2], a0[3], f7[m], f7[m + 1], f7[m - 1], f7[m], zm7[2 * kap], zm7[2 * kap + 1]);
            mma(a1[0], a1[1], a1[2], a1[3], f7[m], f7[m + 1], f7[m - 1], f7[m], z07[2 * kap], z07[2 * kap + 1]);
          }
        }
#pragma unroll
    for (int bk = 0; bk < 4; bk++) {
      sts64(st + 256 * (8 + 2 * bk), pack_bf(a[bk][0][0], a[bk][0][1]), pack_bf(a[bk][1][0], a[bk][1][1]));
      sts64(st + 256 * (9 + 2 * bk), pack_bf(a[bk][0][2], a[bk][0][3]), pack_bf(a[bk][1][2], a[bk][1][3]));
    }
  }
  TS(44);
  {
    const int oh = c < 3 ? 2 * c : -10;
    const uint32_t bx0 = box2w(g - 10, 5, 2 * c - 8), bx1 = box2w(g - 5, 3, 2 * c - 8), bx2 = box2w(g - 10, 5, oh), bx3 = box2w(g - 5, 3, oh);
    const uint32_t lb0 = ((unsigned)(x + 5) < 2u ? kv : 0u) | ((unsigned)(x + 4) < 2u ? kv << 16 : 0u);
    const uint32_t lb1 = ((unsigned)(x - 3) < 2u ? kv : 0u) | ((unsigned)(x - 4) < 2u ? kv << 16 : 0u);
    const int q0 = g - 1, q1 = c < 3 ? g : g - 2;
    uint32_t y0a = ub + U_PAD + (q0 & 1) * U_ODD + 16 * (q0 >> 1) + 4 * c;
    uint32_t y1a = ub + U_PAD + (q1 & 1) * U_ODD + 16 * (q1 >> 1) + 4 * c;
    uint2 a5[10], a3[10];
    const uint32_t aa = tb + T_5 + 4 * (8 + 2 * g - 2 * c);
#pragma unroll
    for (int m = 0; m < 10; m++) { a5[m] = lds64(aa + 32 * m); a3[m] = lds64(aa + 384 + 32 * m); }
    float T[6][4];
#pragma unroll
    for (int i = 0; i < 6; i++) T[i][0] = T[i][1] = T[i][2] = T[i][3] = 0.f;
    uint32_t x5[2] = {0, 0}, x3[2] = {0, 0}, yb[4], lq[4];
    uint32_t lqa = qa, sta = st + 256 * 8;
    uint2 sv;
    auto fetch = [&]() {
      yb[0] = lds32(y0a); yb[1] = lds32(y1a); yb[2] = lds32(y0a + 64); yb[3] = lds32(y1a + 64);
      ldsm4(lq, lqa);
      sv = lds64(min(sta, st + 256 * 15));
      y0a += 128; y1a += 128; lqa += 128; sta += 256;
    };
    fetch();
#pragma unroll 2
    for (int kap = -1; kap < 13; kap++) {
      float yn[2][4];
      mma0(yn[0][0], yn[0][1], yn[0][2], yn[0][3], bx0, bx1, bx2, bx3, yb[0], yb[1]);
      mma0(yn[1][0], yn[1][1], yn[1][2], yn[1][3], bx0, bx1, bx2, bx3, yb[2], yb[3]);
      sts64_p(kap > 0, sta - 256 * 7, pack_bf(T[0][0], T[0][1]), pack_bf(T[0][2], T[0][3]));
#pragma unroll
      for (int i = 0; i < 5; i++)
        mmac_p((unsigned)kap < 12u - i, T[i], a5[2 * i + 1].x, a5[2 * i + 1].y, a5[2 * i].x, a5[2 * i].y, x5[0], x5[1], T[i + 1]);
      const float ci[4] = {bf_lo(sv.x), bf_hi(sv.x), bf_lo(sv.y), bf_hi(sv.y)};
      mmac_p(kap < 7, T[5], lq[0], lq[1], lq[2], lq[3], lb0, lb1, ci);
      fetch();
#pragma unroll
      for (int i = 0; i < 5; i++)
        mma_p((unsigned)kap < 12u - i, T[i], a3[2 * i + 1].x, a3[2 * i + 1].y, a3[2 * i].x, a3[2 * i].y, x3[0], x3[1]);
#pragma unroll
      for (int hh = 0; hh < 2; hh++) { x5[hh] = pack_bf(yn[hh][0], yn[hh][1]); x3[hh] = pack_bf(yn[hh][2], yn[hh][3]); }
    }
  }
  TS(45);
  {
    uint32_t F[66];
    const uint32_t fa = tb + T_D + 32 + 4 * x;
#pragma unroll
    for (int m = 0; m < 66; m++) F[m] = lds32(fa + 32 * m);
    float T[5][4];
#pragma unroll
    for (int i = 0; i < 5; i++) T[i][0] = T[i][1] = T[i][2] = T[i][3] = 0.f;
    uint32_t qd[8][4], held[2] = {0, 0};
    uint32_t qp = qa + 128 * 15, sta = st + 256 * 15;
    uint4* yd = ydst + 19 * 16;
#pragma unroll
    for (int i = 0; i < 8; i++) ldsm4(qd[i], qp - 16 * i);
    uint2 sv = lds64(sta);
    TS(46);
#pragma unroll 1
    for (int be = 15; be >= 0; be--) {
      qp -= 128; sta -= 256;
      const float ci[4] = {bf_lo(sv.x), bf_hi(sv.x), bf_lo(sv.y), bf_hi(sv.y)};
#pragma unroll
      for (int k = 4; k >= 1; k--)
        mmac_p(be + k <= 15, T[k], qd[0][0], qd[0][1], qd[0][2], qd[0][3], F[16 * k + 1], F[16 * k], T[k - 1]);
      mmac(T[0], qd[0][0], qd[0][1], qd[0][2], qd[0][3], F[1], F[0], ci);
      sv = lds64(sta);
      if (be <= 4) sv = make_uint2(0, 0);
#pragma unroll
      for (int i = 1; i < 8; i++) {
#pragma unroll
        for (int k = 3; k >= 0; k--)
          mma_p(k == 0 || be + k <= 15, T[k], qd[i][0], qd[i][1], qd[i][2], qd[i][3], F[16 * k + 2 * i + 1], F[16 * k + 2 * i]);
        ldsm4(qd[i - 1], qp - 16 * (i - 1));
        if (i == 3) {
          const uint32_t w0 = pack_bf(T[4][0], T[4][1]), w1 = pack_bf(T[4][2], T[4][3]);
          st_x_p(be <= 10 && !(be & 1), yd, nz(w0), w1, held[0], held[1]);
          held[0] = w0; held[1] = w1;
          yd -= 16;
        }
      }
      ldsm4(qd[7], qp - 16 * 7);
    }
#pragma unroll
    for (int B = 1; B >= 0; B--)
      st_x(ydst + B * 32, nz(pack_bf(T[2 * B][0], T[2 * B][1])), pack_bf(T[2 * B][2], T[2 * B][3]),
           pack_bf(T[2 * B + 1][0], T[2 * B + 1][1]), pack_bf(T[2 * B + 1][2], T[2 * B + 1][3]));
  }
}

__device__ __forceinline__ void feat(const float (&acc)[48], int j0, const uint32_t (&wf)[4], uint32_t* w) {
  const uint32_t a0 = pack_bf(acc[4 * j0], acc[4 * j0 + 1]), a1 = pack_bf(acc[4 * j0 + 2], acc[4 * j0 + 3]);
  const uint32_t a2 = pack_bf(acc[4 * j0 + 4], acc[4 * j0 + 5]), a3 = pack_bf(acc[4 * j0 + 6], acc[4 * j0 + 7]);
  float p[8];
  mma0(p[0], p[1], p[2], p[3], a0, a1, a2, a3, wf[0], wf[1]);
  mma0(p[4], p[5], p[6], p[7], a0, a1, a2, a3, wf[2], wf[3]);
  w[0] = pack_bf(p[0], p[2]); w[1] = pack_bf(p[1], p[3]); w[2] = pack_bf(p[4], p[6]); w[3] = pack_bf(p[5], p[7]);
}
__device__ __forceinline__ void dual_softmax(const uint32_t* w, uint32_t* e) {
  const float L = 1.4426950408889634f;
  uint32_t mx = bmax2(bmax2(w[0], w[1]), bmax2(w[2], w[3]));
  uint32_t mn = bmin2(bmin2(w[0], w[1]), bmin2(w[2], w[3]));
  mx = bmax2(mx, __shfl_xor_sync(0xffffffffu, mx, 1));
  mn = bmin2(mn, __shfl_xor_sync(0xffffffffu, mn, 1));
  mx = bmax2(mx, __shfl_xor_sync(0xffffffffu, mx, 2));
  mn = bmin2(mn, __shfl_xor_sync(0xffffffffu, mn, 2));
  const float mx0 = __fmul_rn(bf_lo(mx), L), mx1 = __fmul_rn(bf_hi(mx), L);
  const float mn0 = __fmul_rn(bf_lo(mn), L), mn1 = __fmul_rn(bf_hi(mn), L);
  float ep[2][4], em[2][4];
#pragma unroll
  for (int i = 0; i < 4; i++) {
    const float x0 = __fmul_rn(bf_lo(w[i]), L), x1 = __fmul_rn(bf_hi(w[i]), L);
    ep[0][i] = ex2(__fsub_rn(x0, mx0)); em[0][i] = ex2(__fsub_rn(mn0, x0));
    ep[1][i] = ex2(__fsub_rn(x1, mx1)); em[1][i] = ex2(__fsub_rn(mn1, x1));
  }
  __half2 sp = __floats2half2_rn((ep[0][0] + ep[0][1]) + (ep[0][2] + ep[0][3]), (ep[1][0] + ep[1][1]) + (ep[1][2] + ep[1][3]));
  __half2 sm = __floats2half2_rn((em[0][0] + em[0][1]) + (em[0][2] + em[0][3]), (em[1][0] + em[1][1]) + (em[1][2] + em[1][3]));
  sp = __hadd2(sp, __shfl_xor_sync(0xffffffffu, sp, 1));
  sm = __hadd2(sm, __shfl_xor_sync(0xffffffffu, sm, 1));
  sp = __hadd2(sp, __shfl_xor_sync(0xffffffffu, sp, 2));
  sm = __hadd2(sm, __shfl_xor_sync(0xffffffffu, sm, 2));
  const float rp[2] = {rcp(__low2float(sp)), rcp(__high2float(sp))}, rm[2] = {rcp(__low2float(sm)), rcp(__high2float(sm))};
#pragma unroll
  for (int i = 0; i < 4; i++) {
    const int r = i & 1, k = i & 2;
    e[i] = pack_bf(ep[r][k] * rp[r], ep[r][k + 1] * rp[r]);
    e[4 + i] = pack_bf(em[r][k] * rm[r], em[r][k + 1] * rm[r]);
  }
}
__device__ __forceinline__ uint32_t wo_addr(int kb) { return OFF_W + kb * 16384; }

__global__ void __launch_bounds__(NTHREADS, 1)
fused_kernel(const __grid_constant__ CUtensorMap mx, const __grid_constant__ CUtensorMap mw,
             const __grid_constant__ CUtensorMap mo, const __grid_constant__ CUtensorMap mu,
             const __grid_constant__ CUtensorMap mout, const Params P) {
  extern __shared__ uint8_t smem_raw[];
  const uint32_t sb = (smem_u32(smem_raw) + 1023u) & ~1023u;
  const uint32_t bars = sb + OFF_BAR;
  const int tid = threadIdx.x, lane = tid & 31;
  const int warp = __shfl_sync(0xffffffffu, tid >> 5, 0);
  const int b = blockIdx.x, oct = b >> 3, i8 = b & 7;
  const int rt = oct < 8 ? oct : 15 - oct;
  const int hp = (oct >> 3) * 8 + i8;

  if (warp >= 12) {
    asm volatile("setmaxnreg.dec.sync.aligned.u32 32;");
    if (warp == 12) {
#pragma unroll
      for (int i = 0; i < 12; i++) e_init(bars + 8 * i, 1);
      asm volatile("fence.mbarrier_init.release.cluster;" ::: "memory");
      asm volatile("bar.arrive 0, 512;" ::: "memory");
#pragma unroll 1
      for (int kb = 0; kb < 8; kb++) {
        e_expect(bars + 8 * (MB_WFULL + kb), 12288);
        e_tma3d(sb + OFF_W + kb * 12288, &mw, bars + 8 * (MB_WFULL + kb), hp * 32, kb * 64, 0);
        if (kb < 4) {
          e_expect(bars + 8 * (MB_XFULL + kb), 16384);
          e_tma2d(sb + OFF_X + kb * 16384, &mx, bars + 8 * (MB_XFULL + kb), kb * 64, rt * 256);
        }
      }
      e_prefetch(P.x + (size_t)(rt * 256 + hp * 8) * 512, 8192);
      nb_sync(NB_PROD, 64);
#pragma unroll 1
      for (int n = 0; n < 17; n++) {
        if (n < 16) mbar_wait(bars + 8 * (MB_XEMPTY + (n & 3)), (n >> 2) & 1);
        if (n < 12) {
          const int m = n + 4;
          e_expect(bars + 8 * (MB_XFULL + (n & 3)), 16384);
          e_tma2d(sb + OFF_X + (n & 3) * 16384, &mx, bars + 8 * (MB_XFULL + (n & 3)), (m & 7) * 64, rt * 256 + (m >> 3) * 128);
        }
        if (n == STEP_PF) e_prefetch(P.x + (size_t)(rt * 256 + 128 + hp * 8) * 512, 8192);
        if (n == STEP_U) {
          e_expect(bars + 8 * MB_URAW, 16384);
          e_tma5d(sb + OFF_U, &mu, bars + 8 * MB_URAW, i8 * 64, oct * 4);
        }
        if (n == STEP_U + 2) e_prefetch(P.wo + (size_t)b * 2048, 4096);
        if (n >= 9) {
          const int w0 = (0x75436210u >> (4 * (n - 9))) & 7;
          const int col = (hp & 3) * 128 + (w0 >> 2) * 64;
          e_expect(bars + 8 * (MB_WOFULL + w0), 16384);
          e_tma2d(sb + wo_addr(w0), &mo, bars + 8 * (MB_WOFULL + w0), col, w0 * 64);
          e_tma2d(sb + wo_addr(w0) + 8192, &mo, bars + 8 * (MB_WOFULL + w0), col ^ 64, w0 * 64);
        }
      }
    } else {
      unsigned target = 0;
      if (warp == 13) {
#pragma unroll 1
        for (int i = 12; i < 30; i++) e_init(bars + 8 * i, i < MB_XEMPTY ? 1 : (i < MB_CLOSE ? 4 : 12));
        asm volatile("fence.mbarrier_init.release.cluster;" ::: "memory");
        nb_arrive(NB_PROD, 64);
        target = (ld_x32(&g_cnt) & ~(unsigned)(NCTA - 1)) + NCTA;
      }
      asm volatile("bar.sync 0, 512;" ::: "memory");
      uint4* po = g_o + (size_t)(rt * 4 * 32 + hp * 2) * 128;
      uint4* py = g_y + (size_t)b * 1024;
      uint4* pp = g_part + (size_t)(hp * 8 + rt) * 144;
#pragma unroll 1
      for (int i = tid - 416; i < 1024; i += 96) {
        st_x(po + (i >> 8) * 4096 + (i & 255), 0, 0, 0, 0);
        st_x(py + i, 0, 0, 0, 0);
        if (i < 144) st_x(pp + i, 0, 0, 0, 0);
      }
      if (tid == 416) TS1(48);
      mbar_wait(bars + 8 * MB_URAW, 0);
      uint4* dst = g_uT + (size_t)(i8 * 64 + (lane >> 2)) * 256 + (lane & 1) * 128 + oct * 8 + ((lane >> 1) & 1);
#pragma unroll 1
      for (int i = warp - 13; i < 32; i += 3) {
        uint32_t r[4];
        ldsm4t(r, sb + OFF_U + (i >> 3) * 4096 + lane * 128 + (((i ^ lane) & 7) << 4));
        dst[(i & 7) * 2048 + (i >> 3) * 2] = make_uint4(r[0], r[1], r[2], r[3]);
      }
      asm volatile("fence.proxy.async;" ::: "memory");
      nb_sync(NB_INIT, 96);
      if (warp == 13) {
        if (tid == 416) TS1(49);
        sts128(sb + OFF_U + (lane >> 4) * U_CH + ((lane >> 3) & 1) * U_ODD + (lane & 7) * 16, 0, 0, 0, 0);
        sts128(sb + OFF_U + (2 + (lane >> 4)) * U_CH + ((lane >> 3) & 1) * U_ODD + (lane & 7) * 16, 0, 0, 0, 0);
        if (lane == 0) asm volatile("red.release.gpu.global.add.u32 [%0], 1;" ::"l"(&g_cnt) : "memory");
        if (tid == 416) TS1(50);
#pragma unroll 1
        for (int i = 0; i < SPIN_MAX; i++) {
          unsigned v;
          asm volatile("ld.acquire.gpu.global.u32 %0, [%1];" : "=r"(v) : "l"(&g_cnt) : "memory");
          if ((int)(v - target) >= 0) break;
        }
        asm volatile("fence.proxy.async;" ::: "memory");
        __syncwarp();
        if (tid == 416) TS1(51);
        e_expect(bars + 8 * MB_UFULL, 16384);
#pragma unroll 1
        for (int i = 0; i < 8; i++)
          e_bulk(sb + OFF_U + (i >> 1) * U_CH + (i & 1) * U_ODD + U_PAD, g_uT + (size_t)(b * 8 + i) * 128, 2048, bars + 8 * MB_UFULL);
      }
    }
    return;
  }

  const int wg = warp >> 2, w = warp & 3, t = tid & 127;
  const int g = lane >> 2, c = lane & 3;
  const uint32_t tb = sb + OFF_T + w * T_CH;
  const int d = b * 4 + w;
  KgenRaw raw;
  {
    const int o = d * 64 + (wg & 1) * 32 + lane;
    raw.la = __ldg((const uint32_t*)P.logA + o); raw.ai = __ldg((const uint32_t*)P.Aim + o);
    raw.cr = __ldg((const uint32_t*)P.Cre + o); raw.ci = __ldg((const uint32_t*)P.Cim + o);
    raw.ldt = __ldg((const unsigned short*)P.logdt + d);
  }
  asm volatile("bar.sync 0, 512;" ::: "memory");
  asm volatile("setmaxnreg.inc.sync.aligned.u32 160;");
  TS(wg * 16);
  uint32_t wf[2][4];
  {
    const unsigned short* wp = (const unsigned short*)P.wphi + hp * 512 + c * 32 + g;
#pragma unroll
    for (int h = 0; h < 2; h++)
#pragma unroll
      for (int i = 0; i < 4; i++) {
        const int o = h * 256 + (i & 1) * 128 + (i >> 1) * 8;
        wf[h][i] = __byte_perm(__ldg(wp + o), __ldg(wp + o + 16), 0x5410);
      }
  }
  if (wg != 0) {
    float k[5][4], dt, k2048;
    const float dsk = __bfloat162float(P.Dskip[d]);
    kgen_prep(raw, wg & 1, lane, tb, dt, k2048);
    nb_sync(NB_PREP, 256);
    TS(wg * 16 + 1);
#pragma unroll
    for (int j = 0; j < 5; j++) k[j][0] = k[j][1] = k[j][2] = k[j][3] = 0.f;
#pragma unroll 1
    for (int r = 0; r < wg; r++) {
      kgen_round(r ? 12 : (wg - 1) * 6, r ? 4 : 6, lane, tb, bars + 8 * (MB_GDONE + r), k);
      if (r == 0 && lane == 0 && (fu(k[0][0]) & fu(k[1][0]) & fu(k[2][0]) & fu(k[3][0]) & fu(k[4][0])) != 0xffffffffu)
        mbar_arrive(bars + 8 * MB_CLOSE);
    }
    if (wg == 2) {
      TS(34);
      nb_sync(NB_KPART, 256);
      const float sc = 2.f * dt;
#pragma unroll
      for (int j = 0; j < 5; j++) {
        const uint4 v = lds128(tb + j * 512 + lane * 16);
        k[j][0] = (k[j][0] + uf(v.x)) * sc; k[j][1] = (k[j][1] + uf(v.y)) * sc;
        k[j][2] = (k[j][2] + uf(v.z)) * sc; k[j][3] = (k[j][3] + uf(v.w)) * sc;
      }
      k2048 = (k2048 + uf(lds32(tb + 2560))) * sc;
      if (lane == 0) k[0][0] += dsk;
      __syncwarp();
      build_tables(tb, lane, k, k2048);
      TS(35);
      mbar_wait(bars + 8 * MB_UFULL, 0);
      conv_channel(sb + OFF_U + w * U_CH, tb, lane, g_y + (size_t)d * 256 + lane);
      if (lane == 0) mbar_arrive(bars + 8 * MB_BDONE);
      TS(37);
      const int lam = w * 8 + g;
      const uint4* src = g_y + (size_t)(oct * 32 + c * 8) * 256 + i8 * 32 + lam;
      uint4 v[8];
#pragma unroll 1
      for (int it = 0; it < SPIN_MAX; it++) {
        uint32_t m = 0xffffffffu;
#pragma unroll
        for (int i = 0; i < 8; i++) v[i] = ld_x(src + i * 256);
#pragma unroll
        for (int i = 0; i < 8; i++) m = min(m, v[i].x);
        if (__all_sync(0xffffffffu, m != 0)) break;
      }
      __nv_bfloat16* dst = P.out + (size_t)(i8 * 256 + (lam >> 2) * 16 + (lam & 3) * 2) * 1024 + 512 + oct * 32 + c * 8;
#pragma unroll
      for (int i = 0; i < 8; i++) *(uint4*)(dst + (size_t)((i >> 2) * 128 + ((i >> 1) & 1) * 8 + (i & 1)) * 1024) = tr_row(v, i);
      TS(38);
      return;
    }
#pragma unroll
    for (int j = 0; j < 5; j++) sts128(tb + j * 512 + lane * 16, fu(k[j][0]), fu(k[j][1]), fu(k[j][2]), fu(k[j][3]));
    if (lane == 0) sts32(tb + 2560, fu(k2048));
    nb_arrive(NB_KPART, 256);
    mbar_wait(bars + 8 * MB_CLOSE, 0);
    TS(30);
  }

  float acc[2][48];
#pragma unroll 1
  for (int kb = 0; kb < 8; kb++) {
    const int n = wg * 8 + kb;
    mbar_wait(bars + 8 * (MB_WFULL + kb), 0);
    mbar_wait(bars + 8 * (MB_XFULL + (n & 3)), (n >> 2) & 1);
    if (kb == 0) TS(wg * 16 + 2);
    const uint64_t da = mkdesc(sb + OFF_X + (n & 3) * 16384, 16, 1024, 1);
    const uint64_t db = mkdesc(sb + OFF_W + kb * 12288, 4096, 512, 2);
    WG_FENCE();
#pragma unroll
    for (int k = 0; k < 4; k++) {
      wgmma_ss_n96(acc[0], da + 2 * k, db + 64 * k, kb | k);
      wgmma_ss_n96(acc[1], da + 2 * k + 512, db + 64 * k, kb | k);
    }
    WG_COMMIT();
    WG_WAIT(1);
    if (kb > 0 && lane == 0) mbar_arrive(bars + 8 * (MB_XEMPTY + ((n - 1) & 3)));
  }
  WG_WAIT(0);
#pragma unroll 1
  for (int i = 0; i < 2; i++)
    if (lane == 0) mbar_arrive(bars + 8 * (i ? MB_XEMPTY + 3 : MB_GDONE + wg));
  TS(wg * 16 + 3);

  uint32_t pw[32], eq[32];
#pragma unroll
  for (int u = 0; u < 4; u++)
#pragma unroll
    for (int h = 0; h < 2; h++) feat(acc[u & 1], (u < 2 ? 4 : 0) + 2 * h, wf[h], pw + 8 * u + 4 * h);
  {
    uint32_t all = 0xffffffffu;
#pragma unroll
    for (int i = 0; i < 16; i++) all &= pw[2 * i];
    if (wg == 0 && lane == 0 && all != 0xffffffffu) mbar_arrive(bars + 8 * MB_CLOSE);
  }
  mbar_wait(bars + 8 * (MB_GDONE + wg), 0);
  const uint32_t stg0 = sb + OFF_STG0, stg1 = sb + OFF_X + 32768;
  uint32_t sl = (wg ? stg1 : stg0) + w * 3072 + lane * 16;
#pragma unroll
  for (int mt = 0; mt < 2; mt++)
#pragma unroll
    for (int h = 0; h < 2; h++) {
      const float* a = acc[mt] + 32 + 8 * h;
      stsm4(sl + mt * 12288 + 2048 + h * 512, pack_bf(a[0], a[1]), pack_bf(a[2], a[3]), pack_bf(a[4], a[5]), pack_bf(a[6], a[7]));
    }
#pragma unroll 1
  for (int u = 0; u < 4; u++) {
#pragma unroll
    for (int i = 0; i < 16; i++) eq[i] = eq[16 + i];
    dual_softmax(pw, eq + 16);
    dual_softmax(pw + 4, eq + 24);
    if (u < 2) {
#pragma unroll
      for (int i = 0; i < 4; i++) stsm4(sl + i * 512, eq[16 + 4 * i], eq[17 + 4 * i], eq[18 + 4 * i], eq[19 + 4 * i]);
      if (wg) nb_arrive(NB_ST0 + u, 256);
      sl += 12288;
    }
#pragma unroll
    for (int i = 0; i < 24; i++) pw[i] = pw[i + 8];
  }
  TS(wg * 16 + 4);
  const uint32_t kvs = stg0;
  if (wg == 0) {
    nb_sync(NB_WG0, 128);
    mbar_wait(bars + 8 * MB_UFULL, 0);
    mbar_wait(bars + 8 * (MB_GDONE + 1), 0);
    float kv[12];
#pragma unroll
    for (int i = 0; i < 12; i++) kv[i] = 0.f;
    const int mi = lane >> 3;
    const uint32_t ao = w * 512 + (lane & 7) * 16 + ((mi & 1) * 2 + (mi >> 1)) * 128, bo = 2048 + (w >> 1) * 512 + lane * 16;
#pragma unroll 1
    for (int j = 0; j < 4; j++) {
      if (j >= 2) nb_sync(NB_ST0 + j - 2, 256);
      const uint32_t sg = (j >= 2 ? stg1 : stg0) + (j & 1) * 12288;
      uint32_t a[4][4], bb[4][4];
#pragma unroll
      for (int s = 0; s < 4; s++) { ldsm4t(a[s], sg + s * 3072 + ao); ldsm4t(bb[s], sg + s * 3072 + bo); }
#pragma unroll
      for (int s = 0; s < 4; s++) {
        mma(kv[0], kv[1], kv[2], kv[3], a[s][0], a[s][1], a[s][2], a[s][3], bb[s][0], bb[s][1]);
        mma(kv[4], kv[5], kv[6], kv[7], a[s][0], a[s][1], a[s][2], a[s][3], bb[s][2], bb[s][3]);
        mma(kv[8], kv[9], kv[10], kv[11], a[s][0], a[s][1], a[s][2], a[s][3], 0x3F803F80u, 0x3F803F80u);
      }
    }
    uint4* pp = g_part + (size_t)(hp * 8 + rt) * 144;
    st_x(pp + t, nz(pack_bf(kv[0], kv[1])), pack_bf(kv[2], kv[3]), pack_bf(kv[4], kv[5]), pack_bf(kv[6], kv[7]));
    if (c < 2) st_x32((uint32_t*)(pp + 128) + w * 16 + c * 8 + g, nz(fu(c ? kv[10] : kv[8])));
    TS(5);
    const uint4* ps = g_part + (size_t)hp * 8 * 144 + t;
    const uint32_t* zs = (const uint32_t*)(g_part + (size_t)(hp * 8 + (lane >> 4) * 4) * 144 + 128) + w * 16 + (lane & 15);
    uint4 v[8];
    uint32_t zv[4];
#pragma unroll 1
    for (int it = 0; it < SPIN_MAX; it++) {
#pragma unroll
      for (int i = 0; i < 8; i++) v[i] = ld_x(ps + i * 144);
#pragma unroll
      for (int i = 0; i < 4; i++) zv[i] = ld_x32(zs + i * 576);
      uint32_t m = min(min(zv[0], zv[1]), min(zv[2], zv[3]));
#pragma unroll
      for (int i = 0; i < 8; i++) m = min(m, v[i].x);
      if (__all_sync(0xffffffffu, m != 0)) break;
    }
    float s4[4][4];
#pragma unroll
    for (int i = 0; i < 4; i++) s4[i][0] = s4[i][1] = s4[i][2] = s4[i][3] = 0.f;
    const uint32_t eye = (g >> 1) == c ? ((g & 1) ? 0x3F800000u : 0x3F80u) : 0u;
#pragma unroll
    for (int r = 0; r < 8; r++) {
      mma_k8(s4[(r & 1) * 2], v[r].x, v[r].y, eye);
      mma_k8(s4[(r & 1) * 2 + 1], v[r].z, v[r].w, eye);
    }
    float s[8];
#pragma unroll
    for (int i = 0; i < 8; i++) s[i] = s4[i >> 2][i & 3] + s4[2 + (i >> 2)][i & 3];
    float zsum = (uf(zv[0]) + uf(zv[1])) + (uf(zv[2]) + uf(zv[3]));
    zsum += __shfl_xor_sync(0xffffffffu, zsum, 16);
    stsm4(kvs + w * 512 + lane * 16, pack_bf(s[0], s[1]), pack_bf(s[2], s[3]), pack_bf(s[4], s[5]), pack_bf(s[6], s[7]));
    if (lane < 16) sts16(kvs + 2048 + (w * 16 + lane) * 2, pack_bf(zsum, 0.f));
    TS(6);
  }
  nb_sync(NB_KV, 256);
  {
    uint32_t kb_[4][4], zb[8];
#pragma unroll
    for (int i = 0; i < 4; i++) ldsm4t(kb_[i], kvs + i * 512 + lane * 16);
#pragma unroll
    for (int i = 0; i < 8; i++) zb[i] = lds32(kvs + 2048 + i * 16 + c * 4);
    uint4* od = g_o + (size_t)((rt * 4 + wg * 2) * 32 + hp * 2) * 128 + t;
#pragma unroll 1
    for (int mt = 0; mt < 2; mt++) {
#pragma unroll
      for (int h = 0; h < 2; h++) {
        const uint32_t* e = eq + 8 * h;
        float n[8], dn[4];
        mma0(dn[0], dn[1], dn[2], dn[3], e[0], e[1], e[2], e[3], zb[4 * h], zb[4 * h + 1]);
        mma0(n[0], n[1], n[2], n[3], e[0], e[1], e[2], e[3], kb_[2 * h][0], kb_[2 * h][1]);
        mma0(n[4], n[5], n[6], n[7], e[0], e[1], e[2], e[3], kb_[2 * h][2], kb_[2 * h][3]);
        mma(dn[0], dn[1], dn[2], dn[3], e[4], e[5], e[6], e[7], zb[4 * h + 2], zb[4 * h + 3]);
        mma(n[0], n[1], n[2], n[3], e[4], e[5], e[6], e[7], kb_[2 * h + 1][0], kb_[2 * h + 1][1]);
        mma(n[4], n[5], n[6], n[7], e[4], e[5], e[6], e[7], kb_[2 * h + 1][2], kb_[2 * h + 1][3]);
        const float r0 = rcp(dn[0] + 1e-6f), r1 = rcp(dn[2] + 1e-6f);
        st_x(od + h * 128, nz(pack_bf(n[0] * r0, n[1] * r0)), pack_bf(n[2] * r1, n[3] * r1), pack_bf(n[4] * r0, n[5] * r0),
             pack_bf(n[6] * r1, n[7] * r1));
      }
#pragma unroll
      for (int i = 0; i < 16; i++) eq[i] = eq[16 + i];
      od += 4096;
    }
  }
  TS(wg * 16 + 7);
  const int rb = rt * 4 + (hp >> 2);
  const uint4* osrc = g_o + (size_t)(rb * 32 + wg * 16) * 128 + t;
  uint4 af[16];
  {
    const uint32_t* probe = (const uint32_t*)(osrc - lane + (lane & 15) * 128 + (lane >> 4) * 31);
#pragma unroll 1
    for (int it = 0; it < SPIN_MAX; it++) {
      uint32_t m = ld_x32(probe);
#pragma unroll
      for (int i = 0; i < 4; i++) af[i] = ld_x(osrc + i * 128);
#pragma unroll
      for (int i = 0; i < 4; i++) m = min(m, af[i].x);
      if (__all_sync(0xffffffffu, m != 0)) break;
    }
  }
#pragma unroll
  for (int i = 4; i < 16; i++) af[i] = ld_x(osrc + i * 128);
  TS(wg * 16 + 8);
#pragma unroll 1
  for (int j = 0; j < 5; j++) mbar_wait(bars + 8 * (j < 4 ? MB_WOFULL + wg * 4 + j : MB_BDONE), 0);
  TS(wg * 16 + 9);
  float oc[64];
  {
    const uint64_t db = mkdesc(sb + wo_addr(wg * 4), 8192, 1024, 1);
#pragma unroll
    for (int j = 0; j < 4; j++) {
      if (j) {
#pragma unroll 1
        for (int it = 0; it < SPIN_MAX; it++) {
          const uint32_t m = min(min(af[4 * j].x, af[4 * j + 1].x), min(af[4 * j + 2].x, af[4 * j + 3].x));
          if (__all_sync(0xffffffffu, m != 0)) break;
#pragma unroll
          for (int i = 0; i < 4; i++) af[4 * j + i] = ld_x(osrc + (4 * j + i) * 128);
        }
      }
      WG_FENCE();
#pragma unroll
      for (int k = 0; k < 4; k++) wgmma_rs_n128(oc, af[4 * j + k], db + 128 * k + 1024 * j, j | k);
    }
    WG_COMMIT();
    WG_WAIT(0);
  }
  TS(wg * 16 + 10);
  const uint32_t xo = stg1 + wg * 16384 + t * 16, xi = stg1 + (wg ^ 1) * 16384 + t * 16;
#pragma unroll
  for (int i = 0; i < 8; i++) sts128(xo + i * 2048, fu(oc[32 + 4 * i]), fu(oc[33 + 4 * i]), fu(oc[34 + 4 * i]), fu(oc[35 + 4 * i]));
  nb_sync(NB_RED, 256);
  const uint32_t ot = stg0 + warp * 2048;
#pragma unroll
  for (int i = 0; i < 8; i += 2) {
    const uint4 v0 = lds128(xi + i * 2048), v1 = lds128(xi + i * 2048 + 2048);
    stsm4(ot + (lane & 15) * 128 + (((i + (lane >> 4)) ^ (lane & 7)) << 4),
          pack_bf(oc[4 * i] + uf(v0.x), oc[4 * i + 1] + uf(v0.y)), pack_bf(oc[4 * i + 2] + uf(v0.z), oc[4 * i + 3] + uf(v0.w)),
          pack_bf(oc[4 * i + 4] + uf(v1.x), oc[4 * i + 5] + uf(v1.y)), pack_bf(oc[4 * i + 6] + uf(v1.z), oc[4 * i + 7] + uf(v1.w)));
  }
  asm volatile("fence.proxy.async.shared::cta;" ::: "memory");
  __syncwarp();
  e_store2d(&mout, ot, (hp & 3) * 128 + wg * 64, rb * 64 + w * 16);
  TS(wg * 16 + 11);
}

typedef CUresult (*EncodeFn)(CUtensorMap*, CUtensorMapDataType, cuuint32_t, void*, const cuuint64_t*, const cuuint64_t*,
                             const cuuint32_t*, const cuuint32_t*, CUtensorMapInterleave, CUtensorMapSwizzle,
                             CUtensorMapL2promotion, CUtensorMapFloatOOBfill);

}

extern "C" void kernel_launch(void* const* d_in, const int* in_sizes, int n_in, void* d_out, int out_size) {
  (void)in_sizes; (void)n_in; (void)out_size;
  void* fn = nullptr;
  cudaDriverEntryPointQueryResult qr;
  cudaGetDriverEntryPoint("cuTensorMapEncodeTiled", &fn, cudaEnableDefault, &qr);
  EncodeFn enc = (EncodeFn)fn;
  CUtensorMap mx, mw, mo, mu, mout;
  const cuuint32_t es[5] = {1, 1, 1, 1, 1};
  {
    cuuint64_t dims[2] = {512, 2048}, st[1] = {1024};
    cuuint32_t box[2] = {64, 128};
    enc(&mx, CU_TENSOR_MAP_DATA_TYPE_BFLOAT16, 2, d_in[0], dims, st, box, es, CU_TENSOR_MAP_INTERLEAVE_NONE,
        CU_TENSOR_MAP_SWIZZLE_128B, CU_TENSOR_MAP_L2_PROMOTION_L2_128B, CU_TENSOR_MAP_FLOAT_OOB_FILL_NONE);
  }
  {
    cuuint64_t dims[3] = {512, 512, 3}, st[2] = {3072, 1024};
    cuuint32_t box[3] = {32, 64, 3};
    enc(&mw, CU_TENSOR_MAP_DATA_TYPE_BFLOAT16, 3, d_in[1], dims, st, box, es, CU_TENSOR_MAP_INTERLEAVE_NONE,
        CU_TENSOR_MAP_SWIZZLE_64B, CU_TENSOR_MAP_L2_PROMOTION_L2_128B, CU_TENSOR_MAP_FLOAT_OOB_FILL_NONE);
  }
  {
    cuuint64_t dims[2] = {512, 512}, st[1] = {1024};
    cuuint32_t box[2] = {64, 64};
    enc(&mo, CU_TENSOR_MAP_DATA_TYPE_BFLOAT16, 2, d_in[3], dims, st, box, es, CU_TENSOR_MAP_INTERLEAVE_NONE,
        CU_TENSOR_MAP_SWIZZLE_128B, CU_TENSOR_MAP_L2_PROMOTION_L2_128B, CU_TENSOR_MAP_FLOAT_OOB_FILL_NONE);
  }
  {
    cuuint64_t dims[5] = {512, 2, 4, 4, 64}, st[4] = {1024, 8192, 2048, 32768};
    cuuint32_t box[5] = {64, 2, 4, 4, 4};
    enc(&mu, CU_TENSOR_MAP_DATA_TYPE_BFLOAT16, 5, d_in[4], dims, st, box, es, CU_TENSOR_MAP_INTERLEAVE_NONE,
        CU_TENSOR_MAP_SWIZZLE_128B, CU_TENSOR_MAP_L2_PROMOTION_L2_128B, CU_TENSOR_MAP_FLOAT_OOB_FILL_NONE);
  }
  {
    cuuint64_t dims[2] = {1024, 2048}, st[1] = {2048};
    cuuint32_t box[2] = {64, 16};
    enc(&mout, CU_TENSOR_MAP_DATA_TYPE_BFLOAT16, 2, d_out, dims, st, box, es, CU_TENSOR_MAP_INTERLEAVE_NONE,
        CU_TENSOR_MAP_SWIZZLE_128B, CU_TENSOR_MAP_L2_PROMOTION_NONE, CU_TENSOR_MAP_FLOAT_OOB_FILL_NONE);
  }
  Params P;
  P.x = (const __nv_bfloat16*)d_in[0];
  P.wphi = (const __nv_bfloat16*)d_in[2];
  P.wo = (const __nv_bfloat16*)d_in[3];
  P.u = (const __nv_bfloat16*)d_in[4];
  P.logA = (const __nv_bfloat16*)d_in[5];
  P.Aim = (const __nv_bfloat16*)d_in[6];
  P.Cre = (const __nv_bfloat16*)d_in[7];
  P.Cim = (const __nv_bfloat16*)d_in[8];
  P.logdt = (const __nv_bfloat16*)d_in[9];
  P.Dskip = (const __nv_bfloat16*)d_in[10];
  P.out = (__nv_bfloat16*)d_out;
  cudaFuncSetAttribute(fused_kernel, cudaFuncAttributeMaxDynamicSharedMemorySize, SMEM_BYTES);
  fused_kernel<<<NCTA, NTHREADS, SMEM_BYTES>>>(mx, mw, mo, mu, mout, P);
}
```

```cpp
#include <cuda_runtime.h>
#include <cuda_bf16.h>
#include <cuda_fp16.h>
#include <cuda.h>
#include <stdint.h>

#define DBG_TS 0

namespace {

constexpr int NTHREADS = 512;
constexpr int NCTA = 128;
constexpr int OFF_W = 0;
constexpr int OFF_X = 98304;
constexpr int OFF_STG0 = 163840;
constexpr int OFF_U = 188416;
constexpr int U_CH = 4416, U_ODD = 2240, U_PAD = 128;
constexpr int OFF_T = OFF_U + 4 * U_CH;
constexpr int T_CH = 5216;
constexpr int T_D = 0;
constexpr int T_5 = 2144;
constexpr int T_3 = T_5 + 384;
constexpr int T_7 = T_5 + 1024;
constexpr int T_9 = T_7 + 320;
constexpr int T_KC = T_9 + 320;
constexpr int T_ST = T_5 - 1024;
constexpr int OFF_PHI = OFF_T + 4 * T_CH;
constexpr int OFF_BAR = OFF_PHI + 1024;
constexpr int SMEM_BYTES = OFF_BAR + 512;
constexpr uint32_t SB = 1024;
static_assert(T_KC + 2 * 656 <= T_CH, "table size");
static_assert(SMEM_BYTES <= 232448, "smem");
constexpr int MB_FULL = 0  , MB_WO = 16  , MB_UFULL = 18, MB_URAW = 19, MB_EMPTY = 20  ,
              MB_BDONE = 36, MB_CLOSE = 37;
__host__ __device__ constexpr uint32_t BAR(int i) { return SB + OFF_BAR + 8 * i; }
constexpr int NB_WG0 = 1, NB_KPART = 2, NB_ST0 = 3  , NB_KV = 5, NB_RED = 6, NB_INIT = 7, NB_PREP = 8, NB_PROD = 9, NB_RDY = 10;
constexpr int STEP_PF = 0, STEP_U = 2;
constexpr int T_PA = 2144, T_PB = 4192;
constexpr int SPIN_MAX = 1 << 18;

__device__ unsigned g_cnt;
__device__ uint4 g_uT[512 * 256];
__device__ uint4 g_part[16 * 8 * 144];
__device__ uint4 g_o[32 * 32 * 128];
__device__ uint4 g_y[512 * 8 * 32];
extern __shared__ uint8_t smem_raw[];
#define TS(i) do {} while (0)
#define TS1(i) do {} while (0)

__device__ __forceinline__ uint32_t smem_u32(const void* p) { return (uint32_t)__cvta_generic_to_shared(p); }
__device__ __forceinline__ void mbar_arrive(uint32_t b) {
  asm volatile("mbarrier.arrive.shared::cta.b64 _, [%0];" ::"r"(b) : "memory");
}
__device__ __forceinline__ void mbar_wait(uint32_t b) {
  uint32_t done = 0;
#pragma unroll 1
  for (int i = 0; i < SPIN_MAX && !done; i++) {
    asm volatile("{\n.reg .pred p;\nmbarrier.try_wait.parity.shared::cta.b64 p, [%1], 0;\nselp.u32 %0, 1, 0, p;\n}\n"
                 : "=r"(done) : "r"(b) : "memory");
  }
}
__device__ __forceinline__ void mbar_init(uint32_t b, int n) {
  asm volatile("mbarrier.init.shared::cta.b64 [%0], %1;" ::"r"(b), "r"(n) : "memory");
}
__device__ __forceinline__ void mbar_expect(uint32_t b, int bytes) {
  asm volatile("mbarrier.arrive.expect_tx.shared::cta.b64 _, [%0], %1;" ::"r"(b), "r"(bytes) : "memory");
}
__device__ __forceinline__ void nb_sync(int id, int n) { asm volatile("bar.sync %0, %1;" ::"r"(id), "r"(n) : "memory"); }
__device__ __forceinline__ void nb_arrive(int id, int n) { asm volatile("bar.arrive %0, %1;" ::"r"(id), "r"(n) : "memory"); }
#define ELECT "{\n.reg .pred p;\nelect.sync _|p, 0xffffffff;\n@p "
__device__ __forceinline__ void e_expect(uint32_t b, int bytes) {
  asm volatile(ELECT "mbarrier.arrive.expect_tx.shared::cta.b64 _, [%0], %1;\n}\n" ::"r"(b), "r"(bytes) : "memory");
}
__device__ __forceinline__ void e_tma2d(uint32_t dst, const CUtensorMap* m, uint32_t bar, int c0, int c1) {
  asm volatile(ELECT "cp.async.bulk.tensor.2d.shared::cluster.global.mbarrier::complete_tx::bytes [%0], [%1, {%3,%4}], [%2];\n}\n"
               ::"r"(dst), "l"(m), "r"(bar), "r"(c0), "r"(c1) : "memory");
}
__device__ __forceinline__ void e_tma3d(uint32_t dst, const CUtensorMap* m, uint32_t bar, int c0, int c1, int c2) {
  asm volatile(ELECT "cp.async.bulk.tensor.3d.shared::cluster.global.mbarrier::complete_tx::bytes [%0], [%1, {%3,%4,%5}], [%2];\n}\n"
               ::"r"(dst), "l"(m), "r"(bar), "r"(c0), "r"(c1), "r"(c2) : "memory");
}
__device__ __forceinline__ void e_tma5d(uint32_t dst, const CUtensorMap* m, uint32_t bar, int c0, int c4) {
  asm volatile(ELECT "cp.async.bulk.tensor.5d.shared::cluster.global.mbarrier::complete_tx::bytes [%0], [%1, {%3,%5,%5,%5,%4}], [%2];\n}\n"
               ::"r"(dst), "l"(m), "r"(bar), "r"(c0), "r"(c4), "r"(0) : "memory");
}
__device__ __forceinline__ void e_bulk(uint32_t dst, const void* src, int bytes, uint32_t bar) {
  asm volatile(ELECT "cp.async.bulk.shared::cluster.global.mbarrier::complete_tx::bytes [%0], [%1], %2, [%3];\n}\n"
               ::"r"(dst), "l"(src), "r"(bytes), "r"(bar) : "memory");
}
__device__ __forceinline__ void e_prefetch(const void* p, int bytes) {
  asm volatile(ELECT "cp.async.bulk.prefetch.L2.global [%0], %1;\n}\n" ::"l"(p), "r"(bytes) : "memory");
}
__device__ __forceinline__ void e_store2d(const CUtensorMap* m, uint32_t src, int c0, int c1) {
  asm volatile(ELECT "cp.async.bulk.tensor.2d.global.shared::cta.bulk_group [%0, {%2,%3}], [%1];\n"
               "@p cp.async.bulk.commit_group;\n@p cp.async.bulk.wait_group.read 0;\n}\n"
               ::"l"(m), "r"(src), "r"(c0), "r"(c1) : "memory");
}
__host__ __device__ constexpr uint64_t mkdesc(uint32_t addr, uint32_t lbo, uint32_t sbo, int swz) {
  return (uint64_t)((addr & 0x3FFFF) >> 4) | ((uint64_t)(lbo >> 4) << 16) | ((uint64_t)(sbo >> 4) << 32) |
         ((uint64_t)swz << 62);
}
#define WG_FENCE() asm volatile("wgmma.fence.sync.aligned;" ::: "memory")
#define WG_COMMIT() asm volatile("wgmma.commit_group.sync.aligned;" ::: "memory")
#define WG_WAIT(n) asm volatile("wgmma.wait_group.sync.aligned " #n ";" ::: "memory")

__device__ __forceinline__ void mma(float& d0, float& d1, float& d2, float& d3, uint32_t a0, uint32_t a1, uint32_t a2,
                                    uint32_t a3, uint32_t b0, uint32_t b1) {
  asm volatile("mma.sync.aligned.m16n8k16.row.col.f32.bf16.bf16.f32 {%0,%1,%2,%3},{%4,%5,%6,%7},{%8,%9},{%0,%1,%2,%3};"
               : "+f"(d0), "+f"(d1), "+f"(d2), "+f"(d3)
               : "r"(a0), "r"(a1), "r"(a2), "r"(a3), "r"(b0), "r"(b1));
}
__device__ __forceinline__ void mmac(float (&d)[4], uint32_t a0, uint32_t a1, uint32_t a2, uint32_t a3, uint32_t b0,
                                     uint32_t b1, const float (&c)[4]) {
  asm volatile("mma.sync.aligned.m16n8k16.row.col.f32.bf16.bf16.f32 {%0,%1,%2,%3},{%4,%5,%6,%7},{%8,%9},{%10,%11,%12,%13};"
               : "=f"(d[0]), "=f"(d[1]), "=f"(d[2]), "=f"(d[3])
               : "r"(a0), "r"(a1), "r"(a2), "r"(a3), "r"(b0), "r"(b1), "f"(c[0]), "f"(c[1]), "f"(c[2]), "f"(c[3]));
}
__device__ __forceinline__ void mma_p(int p, float (&d)[4], uint32_t a0, uint32_t a1, uint32_t a2, uint32_t a3, uint32_t b0, uint32_t b1) {
  asm volatile("{\n.reg .pred q;\nsetp.ne.b32 q, %10, 0;\n"
               "@q mma.sync.aligned.m16n8k16.row.col.f32.bf16.bf16.f32 {%0,%1,%2,%3},{%4,%5,%6,%7},{%8,%9},{%0,%1,%2,%3};\n}\n"
               : "+f"(d[0]), "+f"(d[1]), "+f"(d[2]), "+f"(d[3])
               : "r"(a0), "r"(a1), "r"(a2), "r"(a3), "r"(b0), "r"(b1), "r"(p));
}
__device__ __forceinline__ void mmac_p(int p, float (&d)[4], uint32_t a0, uint32_t a1, uint32_t a2, uint32_t a3, uint32_t b0,
                                       uint32_t b1, const float (&c)[4]) {
  asm volatile("{\n.reg .pred q;\nsetp.ne.b32 q, %14, 0;\n"
               "@q mma.sync.aligned.m16n8k16.row.col.f32.bf16.bf16.f32 {%0,%1,%2,%3},{%4,%5,%6,%7},{%8,%9},{%10,%11,%12,%13};\n}\n"
               : "+f"(d[0]), "+f"(d[1]), "+f"(d[2]), "+f"(d[3])
               : "r"(a0), "r"(a1), "r"(a2), "r"(a3), "r"(b0), "r"(b1), "f"(c[0]), "f"(c[1]), "f"(c[2]), "f"(c[3]), "r"(p));
}
__device__ __forceinline__ void mma_k8(float (&d)[4], uint32_t a0, uint32_t a1, uint32_t b0) {
  asm volatile("mma.sync.aligned.m16n8k8.row.col.f32.bf16.bf16.f32 {%0,%1,%2,%3},{%4,%5},{%6},{%0,%1,%2,%3};"
               : "+f"(d[0]), "+f"(d[1]), "+f"(d[2]), "+f"(d[3]) : "r"(a0), "r"(a1), "r"(b0));
}
__device__ __forceinline__ void mma0(float& d0, float& d1, float& d2, float& d3, uint32_t a0, uint32_t a1, uint32_t a2,
                                     uint32_t a3, uint32_t b0, uint32_t b1) {
  asm volatile("mma.sync.aligned.m16n8k16.row.col.f32.bf16.bf16.f32 {%0,%1,%2,%3},{%4,%5,%6,%7},{%8,%9},{%10,%10,%10,%10};"
               : "=f"(d0), "=f"(d1), "=f"(d2), "=f"(d3)
               : "r"(a0), "r"(a1), "r"(a2), "r"(a3), "r"(b0), "r"(b1), "f"(0.f));
}
__device__ __forceinline__ uint32_t pack_bf(float lo, float hi) {
  uint32_t r;
  asm("cvt.rn.bf16x2.f32 %0, %1, %2;" : "=r"(r) : "f"(hi), "f"(lo));
  return r;
}
__device__ __forceinline__ float bf_lo(uint32_t w) { return __uint_as_float(w << 16); }
__device__ __forceinline__ float bf_hi(uint32_t w) { return __uint_as_float(w & 0xffff0000u); }
__device__ __forceinline__ float bf_round(float x) { return __bfloat162float(__float2bfloat16_rn(x)); }
__device__ __forceinline__ uint32_t bmax2(uint32_t a, uint32_t b) {
  uint32_t r; asm("max.bf16x2 %0, %1, %2;" : "=r"(r) : "r"(a), "r"(b)); return r;
}
__device__ __forceinline__ uint32_t bmin2(uint32_t a, uint32_t b) {
  uint32_t r; asm("min.bf16x2 %0, %1, %2;" : "=r"(r) : "r"(a), "r"(b)); return r;
}
__device__ __forceinline__ float ex2(float x) { float r; asm("ex2.approx.ftz.f32 %0, %1;" : "=f"(r) : "f"(x)); return r; }
__device__ __forceinline__ float rcp(float x) { float r; asm("rcp.approx.ftz.f32 %0, %1;" : "=f"(r) : "f"(x)); return r; }
__device__ __forceinline__ void ldsm4(uint32_t (&r)[4], uint32_t a) {
  asm volatile("ldmatrix.sync.aligned.m8n8.x4.shared.b16 {%0,%1,%2,%3}, [%4];"
               : "=r"(r[0]), "=r"(r[1]), "=r"(r[2]), "=r"(r[3]) : "r"(a) : "memory");
}
__device__ __forceinline__ void ldsm4t(uint32_t (&r)[4], uint32_t a) {
  asm volatile("ldmatrix.sync.aligned.m8n8.x4.trans.shared.b16 {%0,%1,%2,%3}, [%4];"
               : "=r"(r[0]), "=r"(r[1]), "=r"(r[2]), "=r"(r[3]) : "r"(a) : "memory");
}
__device__ __forceinline__ void stsm4(uint32_t a, uint32_t r0, uint32_t r1, uint32_t r2, uint32_t r3) {
  asm volatile("stmatrix.sync.aligned.m8n8.x4.shared.b16 [%0], {%1,%2,%3,%4};"
               ::"r"(a), "r"(r0), "r"(r1), "r"(r2), "r"(r3) : "memory");
}
__device__ __forceinline__ uint32_t lds32(uint32_t a) {
  uint32_t r; asm volatile("ld.shared.u32 %0, [%1];" : "=r"(r) : "r"(a) : "memory"); return r;
}
__device__ __forceinline__ uint32_t lds16(uint32_t a) {
  uint32_t r; asm volatile("{\n.reg .u16 h;\nld.shared.u16 h, [%1];\ncvt.u32.u16 %0, h;\n}\n" : "=r"(r) : "r"(a) : "memory"); return r;
}
__device__ __forceinline__ uint2 lds64(uint32_t a) {
  uint2 r; asm volatile("ld.shared.v2.u32 {%0,%1}, [%2];" : "=r"(r.x), "=r"(r.y) : "r"(a) : "memory"); return r;
}
__device__ __forceinline__ uint4 lds128(uint32_t a) {
  uint4 r;
  asm volatile("ld.shared.v4.u32 {%0,%1,%2,%3}, [%4];" : "=r"(r.x), "=r"(r.y), "=r"(r.z), "=r"(r.w) : "r"(a) : "memory");
  return r;
}
__device__ __forceinline__ void sts32(uint32_t a, uint32_t v) { asm volatile("st.shared.u32 [%0], %1;" ::"r"(a), "r"(v) : "memory"); }
__device__ __forceinline__ void sts16(uint32_t a, uint32_t v) {
  asm volatile("{\n.reg .u16 h;\ncvt.u16.u32 h, %1;\nst.shared.u16 [%0], h;\n}\n" ::"r"(a), "r"(v) : "memory");
}
__device__ __forceinline__ void sts64(uint32_t a, uint32_t x, uint32_t y) {
  asm volatile("st.shared.v2.u32 [%0], {%1,%2};" ::"r"(a), "r"(x), "r"(y) : "memory");
}
__device__ __forceinline__ void sts128(uint32_t a, uint32_t x, uint32_t y, uint32_t z, uint32_t w) {
  asm volatile("st.shared.v4.u32 [%0], {%1,%2,%3,%4};" ::"r"(a), "r"(x), "r"(y), "r"(z), "r"(w) : "memory");
}
__device__ __forceinline__ uint4 ld_x(const uint4* p) {
  uint4 r;
  asm volatile("{\n.reg .b128 t;\nld.relaxed.gpu.global.b128 t, [%4];\nmov.b128 {%0,%1,%2,%3}, t;\n}\n"
               : "=r"(r.x), "=r"(r.y), "=r"(r.z), "=r"(r.w) : "l"(p) : "memory");
  return r;
}
__device__ __forceinline__ uint32_t ld_x32(const uint32_t* p) {
  uint32_t r; asm volatile("ld.relaxed.gpu.global.u32 %0, [%1];" : "=r"(r) : "l"(p) : "memory"); return r;
}
__device__ __forceinline__ void st_x(uint4* p, uint32_t x, uint32_t y, uint32_t z, uint32_t w) {
  asm volatile("{\n.reg .b128 t;\nmov.b128 t, {%1,%2,%3,%4};\nst.relaxed.gpu.global.b128 [%0], t;\n}\n"
               ::"l"(p), "r"(x), "r"(y), "r"(z), "r"(w) : "memory");
}
__device__ __forceinline__ void st_x_p(int p, uint4* a, uint32_t x, uint32_t y, uint32_t z, uint32_t w) {
  asm volatile("{\n.reg .b128 t;\n.reg .pred q;\nsetp.ne.b32 q, %5, 0;\nmov.b128 t, {%1,%2,%3,%4};\n@q st.relaxed.gpu.global.b128 [%0], t;\n}\n"
               ::"l"(a), "r"(x), "r"(y), "r"(z), "r"(w), "r"(p) : "memory");
}
__device__ __forceinline__ void sts64_p(int p, uint32_t a, uint32_t x, uint32_t y) {
  asm volatile("{\n.reg .pred q;\nsetp.ne.b32 q, %3, 0;\n@q st.shared.v2.u32 [%0], {%1,%2};\n}\n" ::"r"(a), "r"(x), "r"(y), "r"(p) : "memory");
}
__device__ __forceinline__ void st_x32(uint32_t* p, uint32_t x) {
  asm volatile("st.relaxed.gpu.global.u32 [%0], %1;" ::"l"(p), "r"(x) : "memory");
}
__device__ __forceinline__ uint32_t nz(uint32_t w) { return max(w, 1u); }
__device__ __forceinline__ uint32_t fu(float x) { return __float_as_uint(x); }
__device__ __forceinline__ float uf(uint32_t x) { return __uint_as_float(x); }

__device__ __forceinline__ void wgmma_ss_n96(float (&d)[48], uint64_t da, uint64_t db, int sc) {
  asm volatile("{\n.reg .pred p;\nsetp.ne.b32 p, %50, 0;\n"
      "wgmma.mma_async.sync.aligned.m64n96k16.f32.bf16.bf16 "
      "{%0,%1,%2,%3,%4,%5,%6,%7,%8,%9,%10,%11,%12,%13,%14,%15,%16,%17,%18,%19,%20,%21,%22,%23,%24,%25,%26,%27,%28,%29,%30,%31,%32,%33,%34,%35,%36,%37,%38,%39,%40,%41,%42,%43,%44,%45,%46,%47}, "
      "%48, %49, p, 1, 1, 0, 1;\n}\n"
      : "+f"(d[0]), "+f"(d[1]), "+f"(d[2]), "+f"(d[3]), "+f"(d[4]), "+f"(d[5]), "+f"(d[6]), "+f"(d[7]),
        "+f"(d[8]), "+f"(d[9]), "+f"(d[10]), "+f"(d[11]), "+f"(d[12]), "+f"(d[13]), "+f"(d[14]), "+f"(d[15]),
        "+f"(d[16]), "+f"(d[17]), "+f"(d[18]), "+f"(d[19]), "+f"(d[20]), "+f"(d[21]), "+f"(d[22]), "+f"(d[23]),
        "+f"(d[24]), "+f"(d[25]), "+f"(d[26]), "+f"(d[27]), "+f"(d[28]), "+f"(d[29]), "+f"(d[30]), "+f"(d[31]),
        "+f"(d[32]), "+f"(d[33]), "+f"(d[34]), "+f"(d[35]), "+f"(d[36]), "+f"(d[37]), "+f"(d[38]), "+f"(d[39]),
        "+f"(d[40]), "+f"(d[41]), "+f"(d[42]), "+f"(d[43]), "+f"(d[44]), "+f"(d[45]), "+f"(d[46]), "+f"(d[47])
      : "l"(da), "l"(db), "r"(sc));
}

__device__ __forceinline__ void wgmma_rs_n128(float (&d)[64], const uint4& a, uint64_t db, int sc) {
  asm volatile("{\n.reg .pred p;\nsetp.ne.b32 p, %69, 0;\n"
      "wgmma.mma_async.sync.aligned.m64n128k16.f32.bf16.bf16 "
      "{%0,%1,%2,%3,%4,%5,%6,%7,%8,%9,%10,%11,%12,%13,%14,%15,%16,%17,%18,%19,%20,%21,%22,%23,%24,%25,%26,%27,%28,%29,%30,%31,%32,%33,%34,%35,%36,%37,%38,%39,%40,%41,%42,%43,%44,%45,%46,%47,%48,%49,%50,%51,%52,%53,%54,%55,%56,%57,%58,%59,%60,%61,%62,%63}, "
      "{%64,%65,%66,%67}, %68, p, 1, 1, 1;\n}\n"
      : "+f"(d[0]), "+f"(d[1]), "+f"(d[2]), "+f"(d[3]), "+f"(d[4]), "+f"(d[5]), "+f"(d[6]), "+f"(d[7]),
        "+f"(d[8]), "+f"(d[9]), "+f"(d[10]), "+f"(d[11]), "+f"(d[12]), "+f"(d[13]), "+f"(d[14]), "+f"(d[15]),
        "+f"(d[16]), "+f"(d[17]), "+f"(d[18]), "+f"(d[19]), "+f"(d[20]), "+f"(d[21]), "+f"(d[22]), "+f"(d[23]),
        "+f"(d[24]), "+f"(d[25]), "+f"(d[26]), "+f"(d[27]), "+f"(d[28]), "+f"(d[29]), "+f"(d[30]), "+f"(d[31]),
        "+f"(d[32]), "+f"(d[33]), "+f"(d[34]), "+f"(d[35]), "+f"(d[36]), "+f"(d[37]), "+f"(d[38]), "+f"(d[39]),
        "+f"(d[40]), "+f"(d[41]), "+f"(d[42]), "+f"(d[43]), "+f"(d[44]), "+f"(d[45]), "+f"(d[46]), "+f"(d[47]),
        "+f"(d[48]), "+f"(d[49]), "+f"(d[50]), "+f"(d[51]), "+f"(d[52]), "+f"(d[53]), "+f"(d[54]), "+f"(d[55]),
        "+f"(d[56]), "+f"(d[57]), "+f"(d[58]), "+f"(d[59]), "+f"(d[60]), "+f"(d[61]), "+f"(d[62]), "+f"(d[63])
      : "r"(a.x), "r"(a.y), "r"(a.z), "r"(a.w), "l"(db), "r"(sc));
}

struct Params {
  const __nv_bfloat16 *x, *wphi, *wo, *u, *logA, *Aim, *Cre, *Cim, *logdt, *Dskip;
  __nv_bfloat16* out;
};

__device__ __forceinline__ uint4 tr_row(const uint4 (&v)[8], int i) {
  uint32_t o[4];
#pragma unroll
  for (int m = 0; m < 4; m++) {
    const uint4 &ra = v[2 * m], &rb = v[2 * m + 1];
    const int k = i >> 1;
    const uint32_t xa = k == 0 ? ra.x : k == 1 ? ra.y : k == 2 ? ra.z : ra.w;
    const uint32_t xb = k == 0 ? rb.x : k == 1 ? rb.y : k == 2 ? rb.z : rb.w;
    o[m] = __byte_perm(xa, xb, (i & 1) ? 0x7632 : 0x5410);
  }
  return make_uint4(o[0], o[1], o[2], o[3]);
}

struct cpx { float r, i; };
__device__ __forceinline__ cpx cmul(cpx a, cpx b) { return {a.r * b.r - a.i * b.i, a.r * b.i + a.i * b.r}; }
__device__ __forceinline__ cpx csq(cpx a) { return {a.r * a.r - a.i * a.i, 2.f * (a.r * a.i)}; }
__device__ __forceinline__ cpx polar(float e, float t) {
  const float m = ex2(e);
  return {m * __cosf(t), m * __sinf(t)};
}
__device__ __forceinline__ float frac(float t) { return t - rintf(t); }

struct KgenRaw { uint32_t la, ai, cr, ci; unsigned short ldt; };
__device__ __forceinline__ void kgen_prep(KgenRaw r, int half, int lane, uint32_t tb, float& dt, float& k2048) {
  const float TWO_PI = 6.283185307179586f;
  dt = bf_round(expf(bf_lo(r.ldt)));
  float ks = 0.f;
  int m = half * 64 + 2 * lane;
#pragma unroll 1
  for (int j = 0; j < 2; j++, m++) {
    const float a2 = -(bf_round(expf(bf_lo(r.la))) * dt) * 1.4426950408889634f;
    const float f = frac((bf_lo(r.ai) * dt) * 0.15915494309189535f);
    const cpx w64 = polar(a2 * 64.f, frac(f * 64.f) * TWO_PI);
    const cpx we = polar(a2 * 2048.f, frac(f * 2048.f) * TWO_PI);
    ks += bf_lo(r.cr) * we.r - bf_lo(r.ci) * we.i;
    sts128(tb + T_PA + m * 16, fu(a2), fu(f * TWO_PI), fu(w64.r), fu(w64.i));
    sts64(tb + T_PB + m * 8, __byte_perm(r.cr, r.ci, 0x5410), fu(frac(f * 128.f) * TWO_PI));
    r.la >>= 16; r.ai >>= 16; r.cr >>= 16; r.ci >>= 16;
  }
#pragma unroll
  for (int o2 = 16; o2; o2 >>= 1) ks += __shfl_xor_sync(0xffffffffu, ks, o2);
  k2048 = ks;
}
__device__ __forceinline__ void kgen_round(int s0, int cnt, int lane, uint32_t tb, uint32_t open_bar, float (&k)[5][4]) {
  const int g = lane >> 2, c = lane & 3;
  const float pg = (float)g;
  const float n2 = (float)(2 + (g & 1)), m2 = (float)(g & 6), p2 = 128.f * n2 + m2;
  const float n3 = (float)(4 + (g & 3)), m3 = (float)(g & 4), p3 = 128.f * n3 + m3;
  const float n4 = (float)(8 + g), p4 = 128.f * n4;
  uint32_t pa = tb + T_PA + (8 * s0 + c) * 16, pb = tb + T_PB + (8 * s0 + c) * 8;
  uint4 qn[2] = {lds128(pa), lds128(pa + 64)};
  uint2 cn[2] = {lds64(pb), lds64(pb + 32)};
  uint32_t Q[6][14];
#pragma unroll 1
  for (int s = 0; s < cnt; s++) {
    const uint4 qq[2] = {qn[0], qn[1]};
    const uint2 cc[2] = {cn[0], cn[1]};
    pa += 128; pb += 64;
    qn[0] = lds128(pa); qn[1] = lds128(pa + 64);
    cn[0] = lds64(pb); cn[1] = lds64(pb + 32);
    uint32_t o[14];
#pragma unroll
    for (int h = 0; h < 2; h++) {
      const float a2 = uf(qq[h].x), f = uf(qq[h].y), f128 = uf(cc[h].y);
      const cpx w64 = {uf(qq[h].z), uf(qq[h].w)};
      const cpx C = {bf_lo(cc[h].x), bf_hi(cc[h].x)};
      const cpx d1 = polar(a2 * pg, f * pg);
      const cpx t2 = polar(a2 * p2, fmaf(f128, n2, f * m2));
      const cpx t3 = polar(a2 * p3, fmaf(f128, n3, f * m3));
      const cpx s8 = csq(csq(csq(d1)));
      const cpx t4 = polar(a2 * p4, f128 * n4);
      const cpx a0 = cmul(C, s8), a1 = cmul(a0, w64);
      const cpx t1 = cmul(d1, csq(w64));
      o[2 * h] = pack_bf(a0.r, -a0.i);
      o[2 * h + 1] = pack_bf(a1.r, -a1.i);
      o[4 + h] = pack_bf(d1.r, d1.i);
      o[6 + h] = pack_bf(t1.r, t1.i);
      o[8 + h] = pack_bf(t2.r, t2.i);
      o[10 + h] = pack_bf(t3.r, t3.i);
      o[12 + h] = pack_bf(t4.r, t4.i);
    }
#define KQ(i) case i: _Pragma("unroll") for (int e = 0; e < 14; e++) asm volatile("mov.b32 %0, %1;" : "=r"(Q[i][e]) : "r"(o[e])); break;
    switch (s) { KQ(0) KQ(1) KQ(2) KQ(3) KQ(4) default: KQ(5) }
#undef KQ
  }
  TS(40 + (s0 >> 2));
  mbar_wait(open_bar);
#pragma unroll
  for (int s = 0; s < 6; s++)
#pragma unroll
    for (int j = 0; j < 5; j++) mma_p(s < 4 || cnt > 4, k[j], Q[s][0], Q[s][1], Q[s][2], Q[s][3], Q[s][4 + 2 * j], Q[s][5 + 2 * j]);
}

__device__ __forceinline__ void build_tables(uint32_t tb, int lane, float (&k)[5][4], float k2048) {
  const int g = lane >> 2, c = lane & 3;
  const uint32_t kc = tb + T_KC + 16;
  {
    const uint32_t a0 = kc + 16 * g + 4 * c, a2 = kc + 2 * (256 + 4 * g + c);
    const uint32_t a3 = kc + 2 * (384 + 2 * g + 64 * (c & 1) + (c >> 1)), a4 = kc + 2 * (512 + g + 32 * c);
#pragma unroll
    for (int r = 0; r < 2; r++) {
      sts32(a0 + 128 * r, pack_bf(k[0][2 * r], k[0][2 * r + 1]));
      sts32(a0 + 128 * r + 256, pack_bf(k[1][2 * r], k[1][2 * r + 1]));
      const uint32_t w2 = pack_bf(k[2][2 * r], k[2][2 * r + 1]);
      const uint32_t w3 = pack_bf(k[3][2 * r], k[3][2 * r + 1]);
      const uint32_t w4 = pack_bf(k[4][2 * r], k[4][2 * r + 1]);
      sts16(a2 + 64 * r, w2); sts16(a2 + 64 * r + 128, w2 >> 16);
      sts16(a3 + 32 * r, w3); sts16(a3 + 32 * r + 64, w3 >> 16);
      sts16(a4 + 16 * r, w4); sts16(a4 + 16 * r + 32, w4 >> 16);
    }
  }
  if (lane == 0) { sts16(kc + 2 * 640, pack_bf(k2048, 0.f)); sts16(kc - 2, 0); }
  __syncwarp();
  const uint32_t td = tb + T_D + 32;
  {
    const uint4 v = lds128(kc + 16 * lane);
    const uint32_t pv = lds16(kc + 16 * lane - 2);
    sts128(td + 32 * lane, __byte_perm(v.x, pv, 0x5410), __byte_perm(v.x, v.x, 0x1032), __byte_perm(v.y, v.x, 0x7610),
           __byte_perm(v.y, v.y, 0x1032));
    sts128(td + 32 * lane + 16, __byte_perm(v.z, v.y, 0x7610), __byte_perm(v.z, v.z, 0x1032),
           __byte_perm(v.w, v.z, 0x7610), __byte_perm(v.w, v.w, 0x1032));
  }
  {
    const uint2 v = lds64(kc + 512 + 8 * lane);
    const uint32_t k4 = lds16(kc + 512 + 8 * lane + 8);
    const uint32_t pv = lds16(kc + (lane == 0 ? 510 : 512 + 8 * lane));
    const uint32_t k22 = __byte_perm(v.y, v.y, 0x1010);
    sts128(td + 1024 + 32 * lane, __byte_perm(v.x, pv, 0x5410), __byte_perm(v.x, v.x, 0x1010),
           __byte_perm(v.x, v.x, 0x1032), __byte_perm(v.y, v.x, 0x7610));
    sts128(td + 1024 + 32 * lane + 16, k22, k22, __byte_perm(v.y, v.y, 0x1032), __byte_perm(k4, v.y, 0x7610));
  }
  {
    const uint32_t kk = lds16(kc + 2 * 384);
    const uint32_t w = lane < 3 ? (kk | (kk << 16)) : (lane == 3 ? (kk << 16) : 0u);
    if (lane < 24) sts32(td + 4 * (lane < 16 ? 512 + lane : lane - 24), w);
    const uint32_t lo_ = lds16(kc + 2 * 511), le_ = lds16(kc + 2 * 512);
    const uint32_t ja = tb + T_5 + (lane < 16 ? 4 * lane : 256 + 4 * lane);
    sts32(ja, lane == 16 ? (le_ << 16) : 0u);
    sts32(ja + 384, lane == 16 ? (lo_ << 16) : 0u);
    sts32(tb + (lane < 16 ? T_7 : T_9 - 64) + 4 * lane, 0u);
  }
#pragma unroll
  for (int s = 0; s < 2; s++) {
    const uint32_t b = kc + 2 * (s ? 512 : 384) + 8 * lane;
    const uint2 v = lds64(b);
    uint32_t em = lds16(b - 2), e0 = v.x;
    const uint32_t e4 = lds16(b + 8);
    if (lane == 0) { em = 0; e0 = 0; }
    sts64(tb + (s ? T_7 : T_3) + 64 + 8 * lane, __byte_perm(v.x, em, 0x5432), __byte_perm(v.y, v.x, 0x7632));
    sts64(tb + (s ? T_9 : T_5) + 64 + 8 * lane, __byte_perm(v.y, e0, 0x5410), __byte_perm(e4, v.y, 0x5410));
  }
  __syncwarp();
}

__device__ __forceinline__ uint32_t box2w(int lo, int n, int o) {
  return ((unsigned)(o - lo) < (unsigned)n ? 0x3F80u : 0u) | ((unsigned)(o + 1 - lo) < (unsigned)n ? 0x3F800000u : 0u);
}

__device__ __forceinline__ void conv_channel(uint32_t ub, uint32_t tb, int lane, uint4* ydst) {
  const int g = lane >> 2, c = lane & 3, x = g - 2 * c;
  const uint32_t st = tb + T_ST + lane * 8;
  const int mi = lane >> 3;
  const uint32_t qa = ub + U_PAD + 16 * (lane & 7) + ((mi == 0 || mi == 3) ? U_ODD : 0) - (mi == 0 ? 16 : 0);
  const uint32_t kv = lds16(tb + T_KC + 16 + 2 * 512);
  {
    const uint32_t hb = ub + U_PAD + (mi & 1) * U_ODD + 16 * ((lane >> 4) + (lane & 7)) - 16;
    const int oh = c < 2 ? 8 + 2 * c : 2 * c - 8;
    const uint32_t bx0 = box2w(g - 4, 9, 2 * c), bx1 = box2w(g - 3, 7, 2 * c), bx2 = box2w(g - 4, 9, oh), bx3 = box2w(g - 3, 7, oh);
    uint32_t f7[9], f9a[9], f9b[9];
    const uint32_t fa = tb + T_7 + 4 * (8 + x);
#pragma unroll
    for (int m = 0; m < 9; m++) {
      f7[m] = lds32(fa + 32 * m);
      f9b[m] = lds32(fa + 320 + 32 * m);
      f9a[m] = lds32(fa + 316 + 32 * m);
    }
    TS(36);
    uint32_t z09[8], z07[8], zm9[8], zm7[8];
#pragma unroll
    for (int i = 0; i < 8; i++) {
      uint32_t h[4];
      ldsm4(h, hb + 128 * i);
      float y0, y1, y2, y3, w0, w1, w2, w3;
      mma0(y0, y1, y2, y3, bx0, bx1, bx2, bx3, h[2], c < 2 ? h[3] : h[1]);
      mma0(w0, w1, w2, w3, bx0, bx1, bx2, bx3, h[1], c < 2 ? h[2] : h[0]);
      z09[i] = pack_bf(y0, y1); z07[i] = pack_bf(y2, y3);
      zm9[i] = pack_bf(w0, w1); zm7[i] = pack_bf(w2, w3);
    }
    float a[4][2][4];
#pragma unroll
    for (int kap = 0; kap < 4; kap++)
#pragma unroll
      for (int sg = 0; sg < 2; sg++)
#pragma unroll
        for (int bk = 3; bk >= kap; bk--) {
          const int m = 2 * (bk - kap) + 1;
          float(&a0)[4] = a[bk][0];
          float(&a1)[4] = a[bk][1];
          if (sg == 0 && kap == 0) {
            mma0(a0[0], a0[1], a0[2], a0[3], f9a[m], f9a[m + 1], f9a[m - 1], f9a[m], z09[0], z09[1]);
            mma0(a1[0], a1[1], a1[2], a1[3], f9b[m], f9b[m + 1], f9b[m - 1], f9b[m], zm9[0], zm9[1]);
          } else if (sg == 0) {
            mma(a0[0], a0[1], a0[2], a0[3], f9a[m], f9a[m + 1], f9a[m - 1], f9a[m], z09[2 * kap], z09[2 * kap + 1]);
            mma(a1[0], a1[1], a1[2], a1[3], f9b[m], f9b[m + 1], f9b[m - 1], f9b[m], zm9[2 * kap], zm9[2 * kap + 1]);
          } else {
            mma(a0[0], a0[1], a0[2], a0[3], f7[m], f7[m + 1], f7[m - 1], f7[m], zm7[2 * kap], zm7[2 * kap + 1]);
            mma(a1[0], a1[1], a1[2], a1[3], f7[m], f7[m + 1], f7[m - 1], f7[m], z07[2 * kap], z07[2 * kap + 1]);
          }
        }
#pragma unroll
    for (int bk = 0; bk < 4; bk++) {
      sts64(st + 256 * (8 + 2 * bk), pack_bf(a[bk][0][0], a[bk][0][1]), pack_bf(a[bk][1][0], a[bk][1][1]));
      sts64(st + 256 * (9 + 2 * bk), pack_bf(a[bk][0][2], a[bk][0][3]), pack_bf(a[bk][1][2], a[bk][1][3]));
    }
  }
  TS(44);
  {
    const int oh = c < 3 ? 2 * c : -10;
    const uint32_t bx0 = box2w(g - 10, 5, 2 * c - 8), bx1 = box2w(g - 5, 3, 2 * c - 8), bx2 = box2w(g - 10, 5, oh), bx3 = box2w(g - 5, 3, oh);
    const uint32_t lb0 = ((unsigned)(x + 5) < 2u ? kv : 0u) | ((unsigned)(x + 4) < 2u ? kv << 16 : 0u);
    const uint32_t lb1 = ((unsigned)(x - 3) < 2u ? kv : 0u) | ((unsigned)(x - 4) < 2u ? kv << 16 : 0u);
    const int q0 = g - 1, q1 = c < 3 ? g : g - 2;
    uint32_t y0a = ub + U_PAD + (q0 & 1) * U_ODD + 16 * (q0 >> 1) + 4 * c;
    uint32_t y1a = ub + U_PAD + (q1 & 1) * U_ODD + 16 * (q1 >> 1) + 4 * c;
    uint2 a5[10], a3[10];
    const uint32_t aa = tb + T_5 + 4 * (8 + 2 * g - 2 * c);
#pragma unroll
    for (int m = 0; m < 10; m++) { a5[m] = lds64(aa + 32 * m); a3[m] = lds64(aa + 384 + 32 * m); }
    float T[6][4];
#pragma unroll
    for (int i = 0; i < 6; i++) T[i][0] = T[i][1] = T[i][2] = T[i][3] = 0.f;
    uint32_t x5[2] = {0, 0}, x3[2] = {0, 0}, yb[4], lq[4];
    uint32_t lqa = qa, sta = st + 256 * 8;
    uint2 sv;
    auto fetch = [&]() {
      yb[0] = lds32(y0a); yb[1] = lds32(y1a); yb[2] = lds32(y0a + 64); yb[3] = lds32(y1a + 64);
      ldsm4(lq, lqa);
      sv = lds64(min(sta, st + 256 * 15));
      y0a += 128; y1a += 128; lqa += 128; sta += 256;
    };
    fetch();
#pragma unroll 2
    for (int kap = -1; kap < 13; kap++) {
      float yn[2][4];
      mma0(yn[0][0], yn[0][1], yn[0][2], yn[0][3], bx0, bx1, bx2, bx3, yb[0], yb[1]);
      mma0(yn[1][0], yn[1][1], yn[1][2], yn[1][3], bx0, bx1, bx2, bx3, yb[2], yb[3]);
      sts64_p(kap > 0, sta - 256 * 7, pack_bf(T[0][0], T[0][1]), pack_bf(T[0][2], T[0][3]));
#pragma unroll
      for (int i = 0; i < 5; i++)
        mmac_p((unsigned)kap < 12u - i, T[i], a5[2 * i + 1].x, a5[2 * i + 1].y, a5[2 * i].x, a5[2 * i].y, x5[0], x5[1], T[i + 1]);
      const float ci[4] = {bf_lo(sv.x), bf_hi(sv.x), bf_lo(sv.y), bf_hi(sv.y)};
      mmac_p(kap < 7, T[5], lq[0], lq[1], lq[2], lq[3], lb0, lb1, ci);
      fetch();
#pragma unroll
      for (int i = 0; i < 5; i++)
        mma_p((unsigned)kap < 12u - i, T[i], a3[2 * i + 1].x, a3[2 * i + 1].y, a3[2 * i].x, a3[2 * i].y, x3[0], x3[1]);
#pragma unroll
      for (int hh = 0; hh < 2; hh++) { x5[hh] = pack_bf(yn[hh][0], yn[hh][1]); x3[hh] = pack_bf(yn[hh][2], yn[hh][3]); }
    }
  }
  TS(45);
  {
    uint32_t F[66];
    const uint32_t fa = tb + T_D + 32 + 4 * x;
#pragma unroll
    for (int m = 0; m < 66; m++) F[m] = lds32(fa + 32 * m);
    float T[5][4];
#pragma unroll
    for (int i = 0; i < 5; i++) T[i][0] = T[i][1] = T[i][2] = T[i][3] = 0.f;
    uint32_t qd[8][4], held[2] = {0, 0};
    uint32_t qp = qa + 128 * 15, sta = st + 256 * 14;
    uint4* yd = ydst + 19 * 16;
#pragma unroll
    for (int i = 0; i < 6; i++) ldsm4(qd[i], qp - 16 * i);
    uint2 sv = lds64(sta + 256);
    float ci[4] = {bf_lo(sv.x), bf_hi(sv.x), bf_lo(sv.y), bf_hi(sv.y)};
    TS(46);
#pragma unroll 1
    for (int be = 15; be >= 0; be--) {
#pragma unroll
      for (int k = 4; k >= 1; k--)
        mmac_p(be <= 15 - k, T[k], qd[0][0], qd[0][1], qd[0][2], qd[0][3], F[16 * k + 1], F[16 * k], T[k - 1]);
      mmac(T[0], qd[0][0], qd[0][1], qd[0][2], qd[0][3], F[1], F[0], ci);
      ldsm4(qd[6], qp - 16 * 6);
      ldsm4(qd[7], qp - 16 * 7);
      sv = lds64(sta);
#pragma unroll
      for (int i = 1; i < 8; i++) {
#pragma unroll
        for (int k = 3; k >= 0; k--)
          mma_p(k == 0 || be <= 15 - k, T[k], qd[i][0], qd[i][1], qd[i][2], qd[i][3], F[16 * k + 2 * i + 1], F[16 * k + 2 * i]);
        if (i < 7) ldsm4(qd[i - 1], qp - 128 - 16 * (i - 1));
        if (i == 2) {
          const uint32_t w0 = pack_bf(T[4][0], T[4][1]), w1 = pack_bf(T[4][2], T[4][3]);
          st_x_p(be <= 10 && !(be & 1), yd, nz(w0), w1, held[0], held[1]);
          held[0] = w0; held[1] = w1;
        }
        if (i == 4) {
          if (be <= 4) sv = make_uint2(0, 0);
          ci[0] = bf_lo(sv.x); ci[1] = bf_hi(sv.x); ci[2] = bf_lo(sv.y); ci[3] = bf_hi(sv.y);
        }
      }
      qp -= 128; sta -= 256; yd -= 16;
    }
#pragma unroll
    for (int B = 1; B >= 0; B--)
      st_x(ydst + B * 32, nz(pack_bf(T[2 * B][0], T[2 * B][1])), pack_bf(T[2 * B][2], T[2 * B][3]),
           pack_bf(T[2 * B + 1][0], T[2 * B + 1][1]), pack_bf(T[2 * B + 1][2], T[2 * B + 1][3]));
  }
}

__device__ __forceinline__ void feat(const float (&acc)[48], int j0, const uint32_t (&wf)[4], uint32_t* w) {
  const uint32_t a0 = pack_bf(acc[4 * j0], acc[4 * j0 + 1]), a1 = pack_bf(acc[4 * j0 + 2], acc[4 * j0 + 3]);
  const uint32_t a2 = pack_bf(acc[4 * j0 + 4], acc[4 * j0 + 5]), a3 = pack_bf(acc[4 * j0 + 6], acc[4 * j0 + 7]);
  float p[8];
  mma0(p[0], p[1], p[2], p[3], a0, a1, a2, a3, wf[0], wf[1]);
  mma0(p[4], p[5], p[6], p[7], a0, a1, a2, a3, wf[2], wf[3]);
  w[0] = pack_bf(p[0], p[2]); w[1] = pack_bf(p[1], p[3]); w[2] = pack_bf(p[4], p[6]); w[3] = pack_bf(p[5], p[7]);
}
__device__ __forceinline__ void dual_softmax(const uint32_t* w, uint32_t* e) {
  const float L = 1.44268798828125f;
  uint32_t mx = bmax2(bmax2(w[0], w[1]), bmax2(w[2], w[3]));
  uint32_t mn = bmin2(bmin2(w[0], w[1]), bmin2(w[2], w[3]));
  mx = bmax2(mx, __shfl_xor_sync(0xffffffffu, mx, 1));
  mn = bmin2(mn, __shfl_xor_sync(0xffffffffu, mn, 1));
  mx = bmax2(mx, __shfl_xor_sync(0xffffffffu, mx, 2));
  mn = bmin2(mn, __shfl_xor_sync(0xffffffffu, mn, 2));
  const float mx0 = bf_lo(mx) * -L, mx1 = bf_hi(mx) * -L, mn0 = bf_lo(mn) * L, mn1 = bf_hi(mn) * L;
  float ep[2][4], em[2][4];
#pragma unroll
  for (int i = 0; i < 4; i++) {
    const float x0 = bf_lo(w[i]), x1 = bf_hi(w[i]);
    ep[0][i] = ex2(fmaf(x0, L, mx0)); em[0][i] = ex2(fmaf(x0, -L, mn0));
    ep[1][i] = ex2(fmaf(x1, L, mx1)); em[1][i] = ex2(fmaf(x1, -L, mn1));
  }
  __half2 sp = __floats2half2_rn((ep[0][0] + ep[0][1]) + (ep[0][2] + ep[0][3]), (ep[1][0] + ep[1][1]) + (ep[1][2] + ep[1][3]));
  __half2 sm = __floats2half2_rn((em[0][0] + em[0][1]) + (em[0][2] + em[0][3]), (em[1][0] + em[1][1]) + (em[1][2] + em[1][3]));
  sp = __hadd2(sp, __shfl_xor_sync(0xffffffffu, sp, 1));
  sm = __hadd2(sm, __shfl_xor_sync(0xffffffffu, sm, 1));
  sp = __hadd2(sp, __shfl_xor_sync(0xffffffffu, sp, 2));
  sm = __hadd2(sm, __shfl_xor_sync(0xffffffffu, sm, 2));
  const float rp[2] = {rcp(__low2float(sp)), rcp(__high2float(sp))}, rm[2] = {rcp(__low2float(sm)), rcp(__high2float(sm))};
#pragma unroll
  for (int i = 0; i < 4; i++) {
    const int r = i & 1, k = i & 2;
    e[i] = pack_bf(ep[r][k] * rp[r], ep[r][k + 1] * rp[r]);
    e[4 + i] = pack_bf(em[r][k] * rm[r], em[r][k + 1] * rm[r]);
  }
}

__global__ void __launch_bounds__(NTHREADS, 1)
fused_kernel(const __grid_constant__ CUtensorMap mx, const __grid_constant__ CUtensorMap mw,
             const __grid_constant__ CUtensorMap mo, const __grid_constant__ CUtensorMap mu,
             const __grid_constant__ CUtensorMap mout, const Params P) {
  constexpr uint32_t sb = SB;
  const int tid = threadIdx.x, lane = tid & 31;
  const int warp = __shfl_sync(0xffffffffu, tid >> 5, 0);
  const int b = blockIdx.x, oct = b >> 3, i8 = b & 7;
  const int rt = oct < 8 ? oct : 15 - oct;
  const int hp = (oct >> 3) * 8 + i8;

  if (warp >= 12) {
    asm volatile("setmaxnreg.dec.sync.aligned.u32 32;");
    if (warp == 12) {
      if (lane == 0) {
#pragma unroll
        for (int i = 0; i < 16; i++) mbar_init(BAR(MB_FULL + i), 1);
        asm volatile("fence.mbarrier_init.release.cluster;" ::: "memory");
      }
      __syncwarp();
      if (lane < 16) mbar_expect(BAR(MB_FULL) + 8 * lane, lane < 7 ? 28672 : (lane == 7 ? 29696 : 16384));
      __syncwarp();
      nb_arrive(NB_RDY, 256);
      nb_arrive(NB_PREP, 320);
#pragma unroll 1
      for (int kb = 0; kb < 8; kb++) {
        e_tma3d(sb + OFF_W + kb * 12288, &mw, BAR(MB_FULL) + 8 * kb, hp * 32, kb * 64, 0);
        if (kb < 4) e_tma2d(sb + OFF_X + kb * 16384, &mx, BAR(MB_FULL) + 8 * kb, kb * 64, rt * 256);
      }
      e_prefetch(P.x + (size_t)(rt * 256 + hp * 8) * 512, 8192);
      e_bulk(sb + OFF_PHI, P.wphi + hp * 512, 1024, BAR(MB_FULL + 7));
      if (smem_u32(smem_raw) != SB) __trap();
      nb_sync(NB_PROD, 64);
#pragma unroll 1
      for (int n = 0; n < 17; n++) {
        if (n < 16) mbar_wait(BAR(MB_EMPTY) + 8 * n);
        if (n < 12) {
          const int m = n + 4;
          e_tma2d(sb + OFF_X + (n & 3) * 16384, &mx, BAR(MB_FULL) + 8 * m, (m & 7) * 64, rt * 256 + (m >> 3) * 128);
        }
        if (n == STEP_PF) e_prefetch(P.x + (size_t)(rt * 256 + 128 + hp * 8) * 512, 8192);
        if (n == STEP_U) e_tma5d(sb + OFF_U, &mu, BAR(MB_URAW), i8 * 64, oct * 4);
        if (n == STEP_U + 2) e_prefetch(P.wo + (size_t)b * 2048, 4096);
        if (n >= 9) {
          const int w0 = (0x75436210u >> (4 * (n - 9))) & 7;
          const int col = (hp & 3) * 128 + (w0 >> 2) * 64;
          e_tma2d(sb + OFF_W + w0 * 16384, &mo, BAR(MB_WO) + 8 * (w0 >> 2), col, w0 * 64);
          e_tma2d(sb + OFF_W + w0 * 16384 + 8192, &mo, BAR(MB_WO) + 8 * (w0 >> 2), col ^ 64, w0 * 64);
        }
      }
    } else {
      if (warp == 13) {
        if (lane == 0) {
#pragma unroll
          for (int i = 16; i < 38; i++) mbar_init(BAR(i), i < MB_EMPTY ? 1 : (i < MB_CLOSE ? 4 : 12));
          asm volatile("fence.mbarrier_init.release.cluster;" ::: "memory");
          mbar_expect(BAR(MB_WO), 65536);
          mbar_expect(BAR(MB_WO + 1), 65536);
          mbar_expect(BAR(MB_URAW), 16384);
        }
        __syncwarp();
        nb_arrive(NB_PROD, 64);
        nb_arrive(NB_PREP, 320);
      }
      nb_sync(NB_RDY, 256);
      const unsigned cnt0 = ld_x32(&g_cnt);
      uint4* po = g_o + (size_t)(rt * 4 * 32 + hp * 2) * 128;
      uint4* py = g_y + (size_t)b * 1024;
      uint4* pp = g_part + (size_t)(hp * 8 + rt) * 144;
#pragma unroll 1
      for (int i = tid - 416; i < 1024; i += 96) {
        st_x(po + (i >> 8) * 4096 + (i & 255), 0, 0, 0, 0);
        st_x(py + i, 0, 0, 0, 0);
        if (i < 144) st_x(pp + i, 0, 0, 0, 0);
      }
      if (tid == 416) TS1(48);
      mbar_wait(BAR(MB_URAW));
      uint4* dst = g_uT + (size_t)(i8 * 64 + (lane >> 2)) * 256 + (lane & 1) * 128 + oct * 8 + ((lane >> 1) & 1);
#pragma unroll 1
      for (int i = warp - 13; i < 32; i += 3) {
        uint32_t r[4];
        ldsm4t(r, sb + OFF_U + (i >> 3) * 4096 + lane * 128 + (((i ^ lane) & 7) << 4));
        dst[(i & 7) * 2048 + (i >> 3) * 2] = make_uint4(r[0], r[1], r[2], r[3]);
      }
      asm volatile("fence.proxy.async;" ::: "memory");
      nb_sync(NB_INIT, 96);
      if (warp == 13) {
        if (tid == 416) TS1(49);
        sts128(sb + OFF_U + (lane >> 4) * U_CH + ((lane >> 3) & 1) * U_ODD + (lane & 7) * 16, 0, 0, 0, 0);
        sts128(sb + OFF_U + (2 + (lane >> 4)) * U_CH + ((lane >> 3) & 1) * U_ODD + (lane & 7) * 16, 0, 0, 0, 0);
        if (lane == 0) asm volatile("red.release.gpu.global.add.u32 [%0], 1;" ::"l"(&g_cnt) : "memory");
        if (tid == 416) TS1(50);
#pragma unroll 1
        for (int i = 0; i < SPIN_MAX; i++) {
          unsigned v;
          asm volatile("ld.acquire.gpu.global.u32 %0, [%1];" : "=r"(v) : "l"(&g_cnt) : "memory");
          if ((int)(v - ((cnt0 & ~(unsigned)(NCTA - 1)) + NCTA)) >= 0) break;
        }
        asm volatile("fence.proxy.async;" ::: "memory");
        __syncwarp();
        if (tid == 416) TS1(51);
        e_expect(BAR(MB_UFULL), 16384);
#pragma unroll 1
        for (int i = 0; i < 8; i++)
          e_bulk(sb + OFF_U + (i >> 1) * U_CH + (i & 1) * U_ODD + U_PAD, g_uT + (size_t)(b * 8 + i) * 128, 2048, BAR(MB_UFULL));
      }
    }
    return;
  }

  asm volatile("setmaxnreg.inc.sync.aligned.u32 160;");
  const int wg = warp >> 2, w = warp & 3, t = tid & 127;
  const int g = lane >> 2, c = lane & 3;
  const uint32_t tb = sb + OFF_T + w * T_CH;
  const int d = b * 4 + w;
  if (wg != 0) {
    KgenRaw raw;
    const int o = d * 64 + (wg & 1) * 32 + lane;
    raw.la = __ldg((const uint32_t*)P.logA + o); raw.ai = __ldg((const uint32_t*)P.Aim + o);
    raw.cr = __ldg((const uint32_t*)P.Cre + o); raw.ci = __ldg((const uint32_t*)P.Cim + o);
    raw.ldt = __ldg((const unsigned short*)P.logdt + d);
    const unsigned short dsk = __ldg((const unsigned short*)P.Dskip + d);
    float k[5][4], dt, k2048;
    kgen_prep(raw, wg & 1, lane, tb, dt, k2048);
    nb_sync(NB_PREP, 320);
    TS(wg * 16 + 1);
#pragma unroll
    for (int j = 0; j < 5; j++) k[j][0] = k[j][1] = k[j][2] = k[j][3] = 0.f;
#pragma unroll 1
    for (int r = 0; r < wg; r++) {
      kgen_round(r ? 12 : (wg - 1) * 6, r ? 4 : 6, lane, tb, BAR(MB_EMPTY + 7) + 64 * r, k);
      if (r == 0 && lane == 0 && (fu(k[0][0]) & fu(k[1][0]) & fu(k[2][0]) & fu(k[3][0]) & fu(k[4][0])) != 0xffffffffu)
        mbar_arrive(BAR(MB_CLOSE));
    }
    if (wg == 2) {
      TS(34);
      nb_sync(NB_KPART, 256);
      const float sc = 2.f * dt;
#pragma unroll
      for (int j = 0; j < 5; j++) {
        const uint4 v = lds128(tb + j * 512 + lane * 16);
        k[j][0] = (k[j][0] + uf(v.x)) * sc; k[j][1] = (k[j][1] + uf(v.y)) * sc;
        k[j][2] = (k[j][2] + uf(v.z)) * sc; k[j][3] = (k[j][3] + uf(v.w)) * sc;
      }
      k2048 = (k2048 + uf(lds32(tb + 2560))) * sc;
      if (lane == 0) k[0][0] += bf_lo(dsk);
      __syncwarp();
      build_tables(tb, lane, k, k2048);
      TS(35);
      mbar_wait(BAR(MB_UFULL));
      conv_channel(sb + OFF_U + w * U_CH, tb, lane, g_y + (size_t)d * 256 + lane);
      if (lane == 0) mbar_arrive(BAR(MB_BDONE));
      TS(37);
      const int lam = w * 8 + g;
      const uint4* src = g_y + (size_t)(oct * 32 + c * 8) * 256 + i8 * 32 + lam;
      uint4 v[8];
#pragma unroll 1
      for (int it = 0; it < SPIN_MAX; it++) {
        uint32_t m = 0xffffffffu;
#pragma unroll
        for (int i = 0; i < 8; i++) v[i] = ld_x(src + i * 256);
#pragma unroll
        for (int i = 0; i < 8; i++) m = min(m, v[i].x);
        if (__all_sync(0xffffffffu, m != 0)) break;
      }
      __nv_bfloat16* dst = P.out + (size_t)(i8 * 256 + (lam >> 2) * 16 + (lam & 3) * 2) * 1024 + 512 + oct * 32 + c * 8;
#pragma unroll
      for (int i = 0; i < 8; i++) *(uint4*)(dst + (size_t)((i >> 2) * 128 + ((i >> 1) & 1) * 8 + (i & 1)) * 1024) = tr_row(v, i);
      TS(38);
      return;
    }
#pragma unroll
    for (int j = 0; j < 5; j++) sts128(tb + j * 512 + lane * 16, fu(k[j][0]), fu(k[j][1]), fu(k[j][2]), fu(k[j][3]));
    if (lane == 0) sts32(tb + 2560, fu(k2048));
    nb_arrive(NB_KPART, 256);
    mbar_wait(BAR(MB_CLOSE));
    TS(30);
  } else {
    nb_sync(NB_RDY, 256);
    TS(0);
  }

  float acc[2][48];
  {
    uint32_t fb = BAR(MB_FULL) + 64 * wg;
    uint32_t da = (uint32_t)mkdesc(sb + OFF_X, 16, 0, 0), db = (uint32_t)mkdesc(sb + OFF_W, 4096, 0, 0);
    constexpr uint64_t ha = mkdesc(0, 0, 1024, 1), hb = mkdesc(0, 0, 512, 2);
#pragma unroll 1
    for (int kb = 0; kb < 9; kb++) {
      if (kb < 8) {
        mbar_wait(fb);
        if (kb == 0) TS(wg * 16 + 2);
        WG_FENCE();
#pragma unroll
        for (int k = 0; k < 4; k++) {
          wgmma_ss_n96(acc[0], ha | (da + 2 * k), hb | (db + 64 * k), k ? 1 : kb);
          wgmma_ss_n96(acc[1], ha | (da + 2 * k + 512), hb | (db + 64 * k), k ? 1 : kb);
        }
      }
      WG_COMMIT();
      WG_WAIT(1);
      if (kb > 0 && lane == 0) mbar_arrive(fb + 8 * (MB_EMPTY - MB_FULL - 1));
      fb += 8; db += 768;
      da = kb == 3 ? da - 3072 : da + 1024;
    }
    WG_WAIT(0);
  }
  uint32_t wf[2][4];
  ldsm4t(wf[0], sb + OFF_PHI + (lane & 15) * 32 + (lane >> 4) * 16);
  ldsm4t(wf[1], sb + OFF_PHI + 512 + (lane & 15) * 32 + (lane >> 4) * 16);
  TS(wg * 16 + 3);

  uint32_t pw[32], eq[32];
#pragma unroll
  for (int u = 0; u < 4; u++)
#pragma unroll
    for (int h = 0; h < 2; h++) feat(acc[u & 1], (u < 2 ? 4 : 0) + 2 * h, wf[h], pw + 8 * u + 4 * h);
  {
    uint32_t all = 0xffffffffu;
#pragma unroll
    for (int i = 0; i < 16; i++) all &= pw[2 * i];
    if (wg == 0 && lane == 0 && all != 0xffffffffu) mbar_arrive(BAR(MB_CLOSE));
  }
  mbar_wait(BAR(MB_EMPTY + 7) + 64 * wg);
  const uint32_t stg0 = sb + OFF_STG0, stg1 = sb + OFF_X + 32768;
  uint32_t sl = (wg ? stg1 : stg0) + w * 3072 + lane * 16;
#pragma unroll
  for (int mt = 0; mt < 2; mt++)
#pragma unroll
    for (int h = 0; h < 2; h++) {
      const float* a = acc[mt] + 32 + 8 * h;
      stsm4(sl + mt * 12288 + 2048 + h * 512, pack_bf(a[0], a[1]), pack_bf(a[2], a[3]), pack_bf(a[4], a[5]), pack_bf(a[6], a[7]));
    }
#pragma unroll 1
  for (int u = 0; u < 4; u++) {
#pragma unroll
    for (int i = 0; i < 16; i++) eq[i] = eq[16 + i];
    dual_softmax(pw, eq + 16);
    dual_softmax(pw + 4, eq + 24);
    if (u < 2) {
#pragma unroll
      for (int i = 0; i < 4; i++) stsm4(sl + i * 512, eq[16 + 4 * i], eq[17 + 4 * i], eq[18 + 4 * i], eq[19 + 4 * i]);
      if (wg) nb_arrive(NB_ST0 + u, 256);
      sl += 12288;
    }
#pragma unroll
    for (int i = 0; i < 24; i++) pw[i] = pw[i + 8];
  }
  TS(wg * 16 + 4);
  const uint32_t kvs = stg0;
  if (wg == 0) {
    nb_sync(NB_WG0, 128);
    mbar_wait(BAR(MB_UFULL));
    mbar_wait(BAR(MB_EMPTY + 15));
    float kv[12];
#pragma unroll
    for (int i = 0; i < 12; i++) kv[i] = 0.f;
    const int mi = lane >> 3;
    const uint32_t ao = w * 512 + (lane & 7) * 16 + ((mi & 1) * 2 + (mi >> 1)) * 128, bo = 2048 + (w >> 1) * 512 + lane * 16;
#pragma unroll 1
    for (int j = 0; j < 4; j++) {
      if (j >= 2) nb_sync(NB_ST0 + j - 2, 256);
      const uint32_t sg = (j >= 2 ? stg1 : stg0) + (j & 1) * 12288;
      uint32_t a[4][4], bb[4][4];
#pragma unroll
      for (int s = 0; s < 4; s++) { ldsm4t(a[s], sg + s * 3072 + ao); ldsm4t(bb[s], sg + s * 3072 + bo); }
#pragma unroll
      for (int s = 0; s < 4; s++) {
        mma(kv[0], kv[1], kv[2], kv[3], a[s][0], a[s][1], a[s][2], a[s][3], bb[s][0], bb[s][1]);
        mma(kv[4], kv[5], kv[6], kv[7], a[s][0], a[s][1], a[s][2], a[s][3], bb[s][2], bb[s][3]);
        mma(kv[8], kv[9], kv[10], kv[11], a[s][0], a[s][1], a[s][2], a[s][3], 0x3F803F80u, 0x3F803F80u);
      }
    }
    uint4* pp = g_part + (size_t)(hp * 8 + rt) * 144;
    st_x(pp + t, nz(pack_bf(kv[0], kv[1])), pack_bf(kv[2], kv[3]), pack_bf(kv[4], kv[5]), pack_bf(kv[6], kv[7]));
    if (c < 2) st_x32((uint32_t*)(pp + 128) + w * 16 + c * 8 + g, nz(fu(c ? kv[10] : kv[8])));
    TS(5);
    const uint4* ps = g_part + (size_t)hp * 8 * 144 + t;
    const uint32_t* zs = (const uint32_t*)(g_part + (size_t)(hp * 8 + (lane >> 4) * 4) * 144 + 128) + w * 16 + (lane & 15);
    uint4 v[8];
    uint32_t zv[4];
#pragma unroll 1
    for (int it = 0; it < SPIN_MAX; it++) {
#pragma unroll
      for (int i = 0; i < 8; i++) v[i] = ld_x(ps + i * 144);
#pragma unroll
      for (int i = 0; i < 4; i++) zv[i] = ld_x32(zs + i * 576);
      uint32_t m = min(min(zv[0], zv[1]), min(zv[2], zv[3]));
#pragma unroll
      for (int i = 0; i < 8; i++) m = min(m, v[i].x);
      if (__all_sync(0xffffffffu, m != 0)) break;
    }
    float s4[4][4];
#pragma unroll
    for (int i = 0; i < 4; i++) s4[i][0] = s4[i][1] = s4[i][2] = s4[i][3] = 0.f;
    const uint32_t eye = (g >> 1) == c ? ((g & 1) ? 0x3F800000u : 0x3F80u) : 0u;
#pragma unroll
    for (int r = 0; r < 8; r++) {
      mma_k8(s4[(r & 1) * 2], v[r].x, v[r].y, eye);
      mma_k8(s4[(r & 1) * 2 + 1], v[r].z, v[r].w, eye);
    }
    float s[8];
#pragma unroll
    for (int i = 0; i < 8; i++) s[i] = s4[i >> 2][i & 3] + s4[2 + (i >> 2)][i & 3];
    float zsum = (uf(zv[0]) + uf(zv[1])) + (uf(zv[2]) + uf(zv[3]));
    zsum += __shfl_xor_sync(0xffffffffu, zsum, 16);
    stsm4(kvs + w * 512 + lane * 16, pack_bf(s[0], s[1]), pack_bf(s[2], s[3]), pack_bf(s[4], s[5]), pack_bf(s[6], s[7]));
    if (lane < 16) sts16(kvs + 2048 + (w * 16 + lane) * 2, pack_bf(zsum, 0.f));
    TS(6);
  }
  nb_sync(NB_KV, 256);
  {
    uint32_t kb_[4][4], zb[8];
#pragma unroll
    for (int i = 0; i < 4; i++) ldsm4t(kb_[i], kvs + i * 512 + lane * 16);
#pragma unroll
    for (int i = 0; i < 8; i++) zb[i] = lds32(kvs + 2048 + i * 16 + c * 4);
    uint4* od = g_o + (size_t)((rt * 4 + wg * 2) * 32 + hp * 2) * 128 + t;
#pragma unroll 1
    for (int mt = 0; mt < 2; mt++) {
#pragma unroll
      for (int h = 0; h < 2; h++) {
        const uint32_t* e = eq + 8 * h;
        float n[8], dn[4];
        mma0(dn[0], dn[1], dn[2], dn[3], e[0], e[1], e[2], e[3], zb[4 * h], zb[4 * h + 1]);
        mma0(n[0], n[1], n[2], n[3], e[0], e[1], e[2], e[3], kb_[2 * h][0], kb_[2 * h][1]);
        mma0(n[4], n[5], n[6], n[7], e[0], e[1], e[2], e[3], kb_[2 * h][2], kb_[2 * h][3]);
        mma(dn[0], dn[1], dn[2], dn[3], e[4], e[5], e[6], e[7], zb[4 * h + 2], zb[4 * h + 3]);
        mma(n[0], n[1], n[2], n[3], e[4], e[5], e[6], e[7], kb_[2 * h + 1][0], kb_[2 * h + 1][1]);
        mma(n[4], n[5], n[6], n[7], e[4], e[5], e[6], e[7], kb_[2 * h + 1][2], kb_[2 * h + 1][3]);
        const float r0 = rcp(dn[0] + 1e-6f), r1 = rcp(dn[2] + 1e-6f);
        st_x(od + h * 128, nz(pack_bf(n[0] * r0, n[1] * r0)), pack_bf(n[2] * r1, n[3] * r1), pack_bf(n[4] * r0, n[5] * r0),
             pack_bf(n[6] * r1, n[7] * r1));
      }
#pragma unroll
      for (int i = 0; i < 16; i++) eq[i] = eq[16 + i];
      od += 4096;
    }
  }
  TS(wg * 16 + 7);
  const int rb = rt * 4 + (hp >> 2);
  const uint4* osrc = g_o + (size_t)(rb * 32 + wg * 16) * 128 + t;
  uint4 af[16];
  {
    const uint32_t* probe = (const uint32_t*)(osrc - lane + (lane & 15) * 128 + (lane >> 4) * 31);
#pragma unroll 1
    for (int it = 0; it < SPIN_MAX; it++) {
      uint32_t m = ld_x32(probe);
#pragma unroll
      for (int i = 0; i < 4; i++) af[i] = ld_x(osrc + i * 128);
#pragma unroll
      for (int i = 0; i < 4; i++) m = min(m, af[i].x);
      if (__all_sync(0xffffffffu, m != 0)) break;
    }
  }
#pragma unroll
  for (int i = 4; i < 16; i++) af[i] = ld_x(osrc + i * 128);
  TS(wg * 16 + 8);
  mbar_wait(BAR(MB_WO) + 8 * wg);
  mbar_wait(BAR(MB_BDONE));
  TS(wg * 16 + 9);
  float oc[64];
  {
    const uint64_t db = mkdesc(sb + OFF_W, 8192, 1024, 1) + wg * 4096;
#pragma unroll
    for (int j = 0; j < 4; j++) {
      if (j) {
#pragma unroll 1
        for (int it = 0; it < SPIN_MAX; it++) {
          const uint32_t m = min(min(af[4 * j].x, af[4 * j + 1].x), min(af[4 * j + 2].x, af[4 * j + 3].x));
          if (__all_sync(0xffffffffu, m != 0)) break;
#pragma unroll
          for (int i = 0; i < 4; i++) af[4 * j + i] = ld_x(osrc + (4 * j + i) * 128);
        }
      }
      WG_FENCE();
#pragma unroll
      for (int k = 0; k < 4; k++) wgmma_rs_n128(oc, af[4 * j + k], db + 128 * k + 1024 * j, j | k);
    }
    WG_COMMIT();
    WG_WAIT(0);
  }
  TS(wg * 16 + 10);
  const uint32_t xo = stg1 + wg * 16384 + t * 16, xi = stg1 + (wg ^ 1) * 16384 + t * 16;
#pragma unroll
  for (int i = 0; i < 8; i++) sts128(xo + i * 2048, fu(oc[32 + 4 * i]), fu(oc[33 + 4 * i]), fu(oc[34 + 4 * i]), fu(oc[35 + 4 * i]));
  nb_sync(NB_RED, 256);
  const uint32_t ot = stg0 + warp * 2048;
#pragma unroll
  for (int i = 0; i < 8; i += 2) {
    const uint4 v0 = lds128(xi + i * 2048), v1 = lds128(xi + i * 2048 + 2048);
    stsm4(ot + (lane & 15) * 128 + (((i + (lane >> 4)) ^ (lane & 7)) << 4),
          pack_bf(oc[4 * i] + uf(v0.x), oc[4 * i + 1] + uf(v0.y)), pack_bf(oc[4 * i + 2] + uf(v0.z), oc[4 * i + 3] + uf(v0.w)),
          pack_bf(oc[4 * i + 4] + uf(v1.x), oc[4 * i + 5] + uf(v1.y)), pack_bf(oc[4 * i + 6] + uf(v1.z), oc[4 * i + 7] + uf(v1.w)));
  }
  asm volatile("fence.proxy.async.shared::cta;" ::: "memory");
  __syncwarp();
  e_store2d(&mout, ot, (hp & 3) * 128 + wg * 64, rb * 64 + w * 16);
  TS(wg * 16 + 11);
}

typedef CUresult (*EncodeFn)(CUtensorMap*, CUtensorMapDataType, cuuint32_t, void*, const cuuint64_t*, const cuuint64_t*,
                             const cuuint32_t*, const cuuint32_t*, CUtensorMapInterleave, CUtensorMapSwizzle,
                             CUtensorMapL2promotion, CUtensorMapFloatOOBfill);

}

extern "C" void kernel_launch(void* const* d_in, const int* in_sizes, int n_in, void* d_out, int out_size) {
  (void)in_sizes; (void)n_in; (void)out_size;
  void* fn = nullptr;
  cudaDriverEntryPointQueryResult qr;
  cudaGetDriverEntryPoint("cuTensorMapEncodeTiled", &fn, cudaEnableDefault, &qr);
  EncodeFn enc = (EncodeFn)fn;
  CUtensorMap mx, mw, mo, mu, mout;
  const cuuint32_t es[5] = {1, 1, 1, 1, 1};
  {
    cuuint64_t dims[2] = {512, 2048}, st[1] = {1024};
    cuuint32_t box[2] = {64, 128};
    enc(&mx, CU_TENSOR_MAP_DATA_TYPE_BFLOAT16, 2, d_in[0], dims, st, box, es, CU_TENSOR_MAP_INTERLEAVE_NONE,
        CU_TENSOR_MAP_SWIZZLE_128B, CU_TENSOR_MAP_L2_PROMOTION_L2_128B, CU_TENSOR_MAP_FLOAT_OOB_FILL_NONE);
  }
  {
    cuuint64_t dims[3] = {512, 512, 3}, st[2] = {3072, 1024};
    cuuint32_t box[3] = {32, 64, 3};
    enc(&mw, CU_TENSOR_MAP_DATA_TYPE_BFLOAT16, 3, d_in[1], dims, st, box, es, CU_TENSOR_MAP_INTERLEAVE_NONE,
        CU_TENSOR_MAP_SWIZZLE_64B, CU_TENSOR_MAP_L2_PROMOTION_L2_128B, CU_TENSOR_MAP_FLOAT_OOB_FILL_NONE);
  }
  {
    cuuint64_t dims[2] = {512, 512}, st[1] = {1024};
    cuuint32_t box[2] = {64, 64};
    enc(&mo, CU_TENSOR_MAP_DATA_TYPE_BFLOAT16, 2, d_in[3], dims, st, box, es, CU_TENSOR_MAP_INTERLEAVE_NONE,
        CU_TENSOR_MAP_SWIZZLE_128B, CU_TENSOR_MAP_L2_PROMOTION_L2_128B, CU_TENSOR_MAP_FLOAT_OOB_FILL_NONE);
  }
  {
    cuuint64_t dims[5] = {512, 2, 4, 4, 64}, st[4] = {1024, 8192, 2048, 32768};
    cuuint32_t box[5] = {64, 2, 4, 4, 4};
    enc(&mu, CU_TENSOR_MAP_DATA_TYPE_BFLOAT16, 5, d_in[4], dims, st, box, es, CU_TENSOR_MAP_INTERLEAVE_NONE,
        CU_TENSOR_MAP_SWIZZLE_128B, CU_TENSOR_MAP_L2_PROMOTION_L2_128B, CU_TENSOR_MAP_FLOAT_OOB_FILL_NONE);
  }
  {
    cuuint64_t dims[2] = {1024, 2048}, st[1] = {2048};
    cuuint32_t box[2] = {64, 16};
    enc(&mout, CU_TENSOR_MAP_DATA_TYPE_BFLOAT16, 2, d_out, dims, st, box, es, CU_TENSOR_MAP_INTERLEAVE_NONE,
        CU_TENSOR_MAP_SWIZZLE_128B, CU_TENSOR_MAP_L2_PROMOTION_NONE, CU_TENSOR_MAP_FLOAT_OOB_FILL_NONE);
  }
  Params P;
  P.x = (const __nv_bfloat16*)d_in[0];
  P.wphi = (const __nv_bfloat16*)d_in[2];
  P.wo = (const __nv_bfloat16*)d_in[3];
  P.u = (const __nv_bfloat16*)d_in[4];
  P.logA = (const __nv_bfloat16*)d_in[5];
  P.Aim = (const __nv_bfloat16*)d_in[6];
  P.Cre = (const __nv_bfloat16*)d_in[7];
  P.Cim = (const __nv_bfloat16*)d_in[8];
  P.logdt = (const __nv_bfloat16*)d_in[9];
  P.Dskip = (const __nv_bfloat16*)d_in[10];
  P.out = (__nv_bfloat16*)d_out;
  cudaFuncSetAttribute(fused_kernel, cudaFuncAttributeMaxDynamicSharedMemorySize, SMEM_BYTES);
  fused_kernel<<<NCTA, NTHREADS, SMEM_BYTES>>>(mx, mw, mo, mu, mout, P);
}
```

```cpp
#include <cuda_runtime.h>
#include <cuda_bf16.h>
#include <cuda_fp16.h>
#include <cuda.h>
#include <stdint.h>

#define DBG_TS 0

namespace {

constexpr int NTHREADS = 512;
constexpr int NCTA = 128;
constexpr int OFF_W = 0;
constexpr int OFF_X = 98304;
constexpr int OFF_STG0 = 163840;
constexpr int OFF_U = 188416;
constexpr int U_CH = 4416, U_ODD = 2240, U_PAD = 128;
constexpr int OFF_T = OFF_U + 4 * U_CH;
constexpr int T_CH = 5216;
constexpr int T_D = 0;
constexpr int T_5 = 2144;
constexpr int T_3 = T_5 + 384;
constexpr int T_7 = T_5 + 1024;
constexpr int T_9 = T_7 + 320;
constexpr int T_KC = T_9 + 320;
constexpr int T_ST = T_5 - 1024;
constexpr int OFF_PHI = OFF_T + 4 * T_CH;
constexpr int OFF_BAR = OFF_PHI + 1024;
constexpr int SMEM_BYTES = OFF_BAR + 512;
constexpr uint32_t SB = 1024;
static_assert(T_KC + 2 * 656 <= T_CH, "table size");
static_assert(SMEM_BYTES <= 232448, "smem");
constexpr int MB_FULL = 0  , MB_URAW = 16, MB_WO = 17  , MB_UFULL = 19, MB_EMPTY = 20  ,
              MB_BDONE = 36, MB_CLOSE = 37;
__host__ __device__ constexpr uint32_t BAR(int i) { return SB + OFF_BAR + 8 * i; }
constexpr int NB_WG0 = 1, NB_KPART = 2, NB_ST0 = 3  , NB_KV = 5, NB_RED = 6, NB_INIT = 7, NB_PREP = 8, NB_PROD = 9, NB_RDY = 10;
constexpr int STEP_PF = 3, STEP_U = 1;
constexpr int T_PA = 2144, T_PB = 4192;
constexpr int SPIN_MAX = 1 << 18;

__device__ unsigned g_cnt;
__device__ uint4 g_uT[512 * 256];
__device__ uint4 g_part[16 * 8 * 144];
__device__ uint4 g_o[32 * 32 * 128];
__device__ uint4 g_y[512 * 8 * 32];
extern __shared__ uint8_t smem_raw[];
#define TS(i) do {} while (0)
#define TS1(i) do {} while (0)
#define GT(i) do {} while (0)

__device__ __forceinline__ uint32_t smem_u32(const void* p) { return (uint32_t)__cvta_generic_to_shared(p); }
__device__ __forceinline__ void mbar_arrive(uint32_t b) {
  asm volatile("mbarrier.arrive.shared::cta.b64 _, [%0];" ::"r"(b) : "memory");
}
__device__ __forceinline__ void mbar_wait(uint32_t b) {
  uint32_t done = 0;
#pragma unroll 1
  for (int i = 0; i < SPIN_MAX && !done; i++) {
    asm volatile("{\n.reg .pred p;\nmbarrier.try_wait.parity.shared::cta.b64 p, [%1], 0;\nselp.u32 %0, 1, 0, p;\n}\n"
                 : "=r"(done) : "r"(b) : "memory");
  }
}
__device__ __forceinline__ void mbar_init(uint32_t b, int n) {
  asm volatile("mbarrier.init.shared::cta.b64 [%0], %1;" ::"r"(b), "r"(n) : "memory");
}
__device__ __forceinline__ void mbar_expect(uint32_t b, int bytes) {
  asm volatile("mbarrier.arrive.expect_tx.shared::cta.b64 _, [%0], %1;" ::"r"(b), "r"(bytes) : "memory");
}
__device__ __forceinline__ void nb_sync(int id, int n) { asm volatile("bar.sync %0, %1;" ::"r"(id), "r"(n) : "memory"); }
__device__ __forceinline__ void nb_arrive(int id, int n) { asm volatile("bar.arrive %0, %1;" ::"r"(id), "r"(n) : "memory"); }
#define ELECT "{\n.reg .pred p;\nelect.sync _|p, 0xffffffff;\n@p "
__device__ __forceinline__ void e_expect(uint32_t b, int bytes) {
  asm volatile(ELECT "mbarrier.arrive.expect_tx.shared::cta.b64 _, [%0], %1;\n}\n" ::"r"(b), "r"(bytes) : "memory");
}
__device__ __forceinline__ void e_tma2d(uint32_t dst, const CUtensorMap* m, uint32_t bar, int c0, int c1) {
  asm volatile(ELECT "cp.async.bulk.tensor.2d.shared::cluster.global.mbarrier::complete_tx::bytes [%0], [%1, {%3,%4}], [%2];\n}\n"
               ::"r"(dst), "l"(m), "r"(bar), "r"(c0), "r"(c1) : "memory");
}
__device__ __forceinline__ void e_tma3d(uint32_t dst, const CUtensorMap* m, uint32_t bar, int c0, int c1, int c2) {
  asm volatile(ELECT "cp.async.bulk.tensor.3d.shared::cluster.global.mbarrier::complete_tx::bytes [%0], [%1, {%3,%4,%5}], [%2];\n}\n"
               ::"r"(dst), "l"(m), "r"(bar), "r"(c0), "r"(c1), "r"(c2) : "memory");
}
__device__ __forceinline__ void e_tma5d(uint32_t dst, const CUtensorMap* m, uint32_t bar, int c0, int c4) {
  asm volatile(ELECT "cp.async.bulk.tensor.5d.shared::cluster.global.mbarrier::complete_tx::bytes [%0], [%1, {%3,%5,%5,%5,%4}], [%2];\n}\n"
               ::"r"(dst), "l"(m), "r"(bar), "r"(c0), "r"(c4), "r"(0) : "memory");
}
__device__ __forceinline__ void e_bulk(uint32_t dst, const void* src, int bytes, uint32_t bar) {
  asm volatile(ELECT "cp.async.bulk.shared::cluster.global.mbarrier::complete_tx::bytes [%0], [%1], %2, [%3];\n}\n"
               ::"r"(dst), "l"(src), "r"(bytes), "r"(bar) : "memory");
}
__device__ __forceinline__ void e_prefetch(const void* p, int bytes) {
  asm volatile(ELECT "cp.async.bulk.prefetch.L2.global [%0], %1;\n}\n" ::"l"(p), "r"(bytes) : "memory");
}
__device__ __forceinline__ void e_store2d(const CUtensorMap* m, uint32_t src, int c0, int c1) {
  asm volatile(ELECT "cp.async.bulk.tensor.2d.global.shared::cta.bulk_group [%0, {%2,%3}], [%1];\n"
               "@p cp.async.bulk.commit_group;\n@p cp.async.bulk.wait_group.read 0;\n}\n"
               ::"l"(m), "r"(src), "r"(c0), "r"(c1) : "memory");
}
__host__ __device__ constexpr uint64_t mkdesc(uint32_t addr, uint32_t lbo, uint32_t sbo, int swz) {
  return (uint64_t)((addr & 0x3FFFF) >> 4) | ((uint64_t)(lbo >> 4) << 16) | ((uint64_t)(sbo >> 4) << 32) |
         ((uint64_t)swz << 62);
}
#define WG_FENCE() asm volatile("wgmma.fence.sync.aligned;" ::: "memory")
#define WG_COMMIT() asm volatile("wgmma.commit_group.sync.aligned;" ::: "memory")
#define WG_WAIT(n) asm volatile("wgmma.wait_group.sync.aligned " #n ";" ::: "memory")

__device__ __forceinline__ void mma(float& d0, float& d1, float& d2, float& d3, uint32_t a0, uint32_t a1, uint32_t a2,
                                    uint32_t a3, uint32_t b0, uint32_t b1) {
  asm volatile("mma.sync.aligned.m16n8k16.row.col.f32.bf16.bf16.f32 {%0,%1,%2,%3},{%4,%5,%6,%7},{%8,%9},{%0,%1,%2,%3};"
               : "+f"(d0), "+f"(d1), "+f"(d2), "+f"(d3)
               : "r"(a0), "r"(a1), "r"(a2), "r"(a3), "r"(b0), "r"(b1));
}
__device__ __forceinline__ void mmac(float (&d)[4], uint32_t a0, uint32_t a1, uint32_t a2, uint32_t a3, uint32_t b0,
                                     uint32_t b1, const float (&c)[4]) {
  asm volatile("mma.sync.aligned.m16n8k16.row.col.f32.bf16.bf16.f32 {%0,%1,%2,%3},{%4,%5,%6,%7},{%8,%9},{%10,%11,%12,%13};"
               : "=f"(d[0]), "=f"(d[1]), "=f"(d[2]), "=f"(d[3])
               : "r"(a0), "r"(a1), "r"(a2), "r"(a3), "r"(b0), "r"(b1), "f"(c[0]), "f"(c[1]), "f"(c[2]), "f"(c[3]));
}
__device__ __forceinline__ void mma_p(int p, float (&d)[4], uint32_t a0, uint32_t a1, uint32_t a2, uint32_t a3, uint32_t b0, uint32_t b1) {
  asm volatile("{\n.reg .pred q;\nsetp.ne.b32 q, %10, 0;\n"
               "@q mma.sync.aligned.m16n8k16.row.col.f32.bf16.bf16.f32 {%0,%1,%2,%3},{%4,%5,%6,%7},{%8,%9},{%0,%1,%2,%3};\n}\n"
               : "+f"(d[0]), "+f"(d[1]), "+f"(d[2]), "+f"(d[3])
               : "r"(a0), "r"(a1), "r"(a2), "r"(a3), "r"(b0), "r"(b1), "r"(p));
}
__device__ __forceinline__ void mmac_p(int p, float (&d)[4], uint32_t a0, uint32_t a1, uint32_t a2, uint32_t a3, uint32_t b0,
                                       uint32_t b1, const float (&c)[4]) {
  asm volatile("{\n.reg .pred q;\nsetp.ne.b32 q, %14, 0;\n"
               "@q mma.sync.aligned.m16n8k16.row.col.f32.bf16.bf16.f32 {%0,%1,%2,%3},{%4,%5,%6,%7},{%8,%9},{%10,%11,%12,%13};\n}\n"
               : "+f"(d[0]), "+f"(d[1]), "+f"(d[2]), "+f"(d[3])
               : "r"(a0), "r"(a1), "r"(a2), "r"(a3), "r"(b0), "r"(b1), "f"(c[0]), "f"(c[1]), "f"(c[2]), "f"(c[3]), "r"(p));
}
__device__ __forceinline__ void mma_k8(float (&d)[4], uint32_t a0, uint32_t a1, uint32_t b0) {
  asm volatile("mma.sync.aligned.m16n8k8.row.col.f32.bf16.bf16.f32 {%0,%1,%2,%3},{%4,%5},{%6},{%0,%1,%2,%3};"
               : "+f"(d[0]), "+f"(d[1]), "+f"(d[2]), "+f"(d[3]) : "r"(a0), "r"(a1), "r"(b0));
}
__device__ __forceinline__ void mma0(float& d0, float& d1, float& d2, float& d3, uint32_t a0, uint32_t a1, uint32_t a2,
                                     uint32_t a3, uint32_t b0, uint32_t b1) {
  asm volatile("mma.sync.aligned.m16n8k16.row.col.f32.bf16.bf16.f32 {%0,%1,%2,%3},{%4,%5,%6,%7},{%8,%9},{%10,%10,%10,%10};"
               : "=f"(d0), "=f"(d1), "=f"(d2), "=f"(d3)
               : "r"(a0), "r"(a1), "r"(a2), "r"(a3), "r"(b0), "r"(b1), "f"(0.f));
}
__device__ __forceinline__ uint32_t pack_bf(float lo, float hi) {
  uint32_t r;
  asm("cvt.rn.bf16x2.f32 %0, %1, %2;" : "=r"(r) : "f"(hi), "f"(lo));
  return r;
}
__device__ __forceinline__ float bf_lo(uint32_t w) { return __uint_as_float(w << 16); }
__device__ __forceinline__ float bf_hi(uint32_t w) { return __uint_as_float(w & 0xffff0000u); }
__device__ __forceinline__ float bf_round(float x) { return __bfloat162float(__float2bfloat16_rn(x)); }
__device__ __forceinline__ uint32_t bmax2(uint32_t a, uint32_t b) {
  uint32_t r; asm("max.bf16x2 %0, %1, %2;" : "=r"(r) : "r"(a), "r"(b)); return r;
}
__device__ __forceinline__ uint32_t bmin2(uint32_t a, uint32_t b) {
  uint32_t r; asm("min.bf16x2 %0, %1, %2;" : "=r"(r) : "r"(a), "r"(b)); return r;
}
__device__ __forceinline__ float ex2(float x) { float r; asm("ex2.approx.ftz.f32 %0, %1;" : "=f"(r) : "f"(x)); return r; }
__device__ __forceinline__ float rcp(float x) { float r; asm("rcp.approx.ftz.f32 %0, %1;" : "=f"(r) : "f"(x)); return r; }
__device__ __forceinline__ void ldsm4(uint32_t (&r)[4], uint32_t a) {
  asm volatile("ldmatrix.sync.aligned.m8n8.x4.shared.b16 {%0,%1,%2,%3}, [%4];"
               : "=r"(r[0]), "=r"(r[1]), "=r"(r[2]), "=r"(r[3]) : "r"(a) : "memory");
}
__device__ __forceinline__ void ldsm4t(uint32_t (&r)[4], uint32_t a) {
  asm volatile("ldmatrix.sync.aligned.m8n8.x4.trans.shared.b16 {%0,%1,%2,%3}, [%4];"
               : "=r"(r[0]), "=r"(r[1]), "=r"(r[2]), "=r"(r[3]) : "r"(a) : "memory");
}
__device__ __forceinline__ void stsm4(uint32_t a, uint32_t r0, uint32_t r1, uint32_t r2, uint32_t r3) {
  asm volatile("stmatrix.sync.aligned.m8n8.x4.shared.b16 [%0], {%1,%2,%3,%4};"
               ::"r"(a), "r"(r0), "r"(r1), "r"(r2), "r"(r3) : "memory");
}
__device__ __forceinline__ uint32_t lds32(uint32_t a) {
  uint32_t r; asm volatile("ld.shared.u32 %0, [%1];" : "=r"(r) : "r"(a) : "memory"); return r;
}
__device__ __forceinline__ uint32_t lds16(uint32_t a) {
  uint32_t r; asm volatile("{\n.reg .u16 h;\nld.shared.u16 h, [%1];\ncvt.u32.u16 %0, h;\n}\n" : "=r"(r) : "r"(a) : "memory"); return r;
}
__device__ __forceinline__ uint2 lds64(uint32_t a) {
  uint2 r; asm volatile("ld.shared.v2.u32 {%0,%1}, [%2];" : "=r"(r.x), "=r"(r.y) : "r"(a) : "memory"); return r;
}
__device__ __forceinline__ uint4 lds128(uint32_t a) {
  uint4 r;
  asm volatile("ld.shared.v4.u32 {%0,%1,%2,%3}, [%4];" : "=r"(r.x), "=r"(r.y), "=r"(r.z), "=r"(r.w) : "r"(a) : "memory");
  return r;
}
__device__ __forceinline__ void sts32(uint32_t a, uint32_t v) { asm volatile("st.shared.u32 [%0], %1;" ::"r"(a), "r"(v) : "memory"); }
__device__ __forceinline__ void sts16(uint32_t a, uint32_t v) {
  asm volatile("{\n.reg .u16 h;\ncvt.u16.u32 h, %1;\nst.shared.u16 [%0], h;\n}\n" ::"r"(a), "r"(v) : "memory");
}
__device__ __forceinline__ void sts64(uint32_t a, uint32_t x, uint32_t y) {
  asm volatile("st.shared.v2.u32 [%0], {%1,%2};" ::"r"(a), "r"(x), "r"(y) : "memory");
}
__device__ __forceinline__ void sts128(uint32_t a, uint32_t x, uint32_t y, uint32_t z, uint32_t w) {
  asm volatile("st.shared.v4.u32 [%0], {%1,%2,%3,%4};" ::"r"(a), "r"(x), "r"(y), "r"(z), "r"(w) : "memory");
}
__device__ __forceinline__ uint4 ld_x(const uint4* p) {
  uint4 r;
  asm volatile("{\n.reg .b128 t;\nld.relaxed.gpu.global.b128 t, [%4];\nmov.b128 {%0,%1,%2,%3}, t;\n}\n"
               : "=r"(r.x), "=r"(r.y), "=r"(r.z), "=r"(r.w) : "l"(p) : "memory");
  return r;
}
__device__ __forceinline__ uint32_t ld_x32(const uint32_t* p) {
  uint32_t r; asm volatile("ld.relaxed.gpu.global.u32 %0, [%1];" : "=r"(r) : "l"(p) : "memory"); return r;
}
__device__ __forceinline__ void st_x(uint4* p, uint32_t x, uint32_t y, uint32_t z, uint32_t w) {
  asm volatile("{\n.reg .b128 t;\nmov.b128 t, {%1,%2,%3,%4};\nst.relaxed.gpu.global.b128 [%0], t;\n}\n"
               ::"l"(p), "r"(x), "r"(y), "r"(z), "r"(w) : "memory");
}
__device__ __forceinline__ void st_x_p(int p, uint4* a, uint32_t x, uint32_t y, uint32_t z, uint32_t w) {
  asm volatile("{\n.reg .b128 t;\n.reg .pred q;\nsetp.ne.b32 q, %5, 0;\nmov.b128 t, {%1,%2,%3,%4};\n@q st.relaxed.gpu.global.b128 [%0], t;\n}\n"
               ::"l"(a), "r"(x), "r"(y), "r"(z), "r"(w), "r"(p) : "memory");
}
__device__ __forceinline__ void sts64_p(int p, uint32_t a, uint32_t x, uint32_t y) {
  asm volatile("{\n.reg .pred q;\nsetp.ne.b32 q, %3, 0;\n@q st.shared.v2.u32 [%0], {%1,%2};\n}\n" ::"r"(a), "r"(x), "r"(y), "r"(p) : "memory");
}
__device__ __forceinline__ void st_x32(uint32_t* p, uint32_t x) {
  asm volatile("st.relaxed.gpu.global.u32 [%0], %1;" ::"l"(p), "r"(x) : "memory");
}
__device__ __forceinline__ uint32_t nz(uint32_t w) { return max(w, 1u); }
__device__ __forceinline__ uint32_t fu(float x) { return __float_as_uint(x); }
__device__ __forceinline__ float uf(uint32_t x) { return __uint_as_float(x); }

__device__ __forceinline__ void wgmma_ss_n96(float (&d)[48], uint64_t da, uint64_t db, int sc) {
  asm volatile("{\n.reg .pred p;\nsetp.ne.b32 p, %50, 0;\n"
      "wgmma.mma_async.sync.aligned.m64n96k16.f32.bf16.bf16 "
      "{%0,%1,%2,%3,%4,%5,%6,%7,%8,%9,%10,%11,%12,%13,%14,%15,%16,%17,%18,%19,%20,%21,%22,%23,%24,%25,%26,%27,%28,%29,%30,%31,%32,%33,%34,%35,%36,%37,%38,%39,%40,%41,%42,%43,%44,%45,%46,%47}, "
      "%48, %49, p, 1, 1, 0, 1;\n}\n"
      : "+f"(d[0]), "+f"(d[1]), "+f"(d[2]), "+f"(d[3]), "+f"(d[4]), "+f"(d[5]), "+f"(d[6]), "+f"(d[7]),
        "+f"(d[8]), "+f"(d[9]), "+f"(d[10]), "+f"(d[11]), "+f"(d[12]), "+f"(d[13]), "+f"(d[14]), "+f"(d[15]),
        "+f"(d[16]), "+f"(d[17]), "+f"(d[18]), "+f"(d[19]), "+f"(d[20]), "+f"(d[21]), "+f"(d[22]), "+f"(d[23]),
        "+f"(d[24]), "+f"(d[25]), "+f"(d[26]), "+f"(d[27]), "+f"(d[28]), "+f"(d[29]), "+f"(d[30]), "+f"(d[31]),
        "+f"(d[32]), "+f"(d[33]), "+f"(d[34]), "+f"(d[35]), "+f"(d[36]), "+f"(d[37]), "+f"(d[38]), "+f"(d[39]),
        "+f"(d[40]), "+f"(d[41]), "+f"(d[42]), "+f"(d[43]), "+f"(d[44]), "+f"(d[45]), "+f"(d[46]), "+f"(d[47])
      : "l"(da), "l"(db), "r"(sc));
}

__device__ __forceinline__ void wgmma_rs_n128(float (&d)[64], const uint4& a, uint64_t db, int sc) {
  asm volatile("{\n.reg .pred p;\nsetp.ne.b32 p, %69, 0;\n"
      "wgmma.mma_async.sync.aligned.m64n128k16.f32.bf16.bf16 "
      "{%0,%1,%2,%3,%4,%5,%6,%7,%8,%9,%10,%11,%12,%13,%14,%15,%16,%17,%18,%19,%20,%21,%22,%23,%24,%25,%26,%27,%28,%29,%30,%31,%32,%33,%34,%35,%36,%37,%38,%39,%40,%41,%42,%43,%44,%45,%46,%47,%48,%49,%50,%51,%52,%53,%54,%55,%56,%57,%58,%59,%60,%61,%62,%63}, "
      "{%64,%65,%66,%67}, %68, p, 1, 1, 1;\n}\n"
      : "+f"(d[0]), "+f"(d[1]), "+f"(d[2]), "+f"(d[3]), "+f"(d[4]), "+f"(d[5]), "+f"(d[6]), "+f"(d[7]),
        "+f"(d[8]), "+f"(d[9]), "+f"(d[10]), "+f"(d[11]), "+f"(d[12]), "+f"(d[13]), "+f"(d[14]), "+f"(d[15]),
        "+f"(d[16]), "+f"(d[17]), "+f"(d[18]), "+f"(d[19]), "+f"(d[20]), "+f"(d[21]), "+f"(d[22]), "+f"(d[23]),
        "+f"(d[24]), "+f"(d[25]), "+f"(d[26]), "+f"(d[27]), "+f"(d[28]), "+f"(d[29]), "+f"(d[30]), "+f"(d[31]),
        "+f"(d[32]), "+f"(d[33]), "+f"(d[34]), "+f"(d[35]), "+f"(d[36]), "+f"(d[37]), "+f"(d[38]), "+f"(d[39]),
        "+f"(d[40]), "+f"(d[41]), "+f"(d[42]), "+f"(d[43]), "+f"(d[44]), "+f"(d[45]), "+f"(d[46]), "+f"(d[47]),
        "+f"(d[48]), "+f"(d[49]), "+f"(d[50]), "+f"(d[51]), "+f"(d[52]), "+f"(d[53]), "+f"(d[54]), "+f"(d[55]),
        "+f"(d[56]), "+f"(d[57]), "+f"(d[58]), "+f"(d[59]), "+f"(d[60]), "+f"(d[61]), "+f"(d[62]), "+f"(d[63])
      : "r"(a.x), "r"(a.y), "r"(a.z), "r"(a.w), "l"(db), "r"(sc));
}

struct Params {
  const __nv_bfloat16 *x, *wphi, *wo, *u, *logA, *Aim, *Cre, *Cim, *logdt, *Dskip;
  __nv_bfloat16* out;
};

__device__ __forceinline__ uint4 tr_row(const uint4 (&v)[8], int i) {
  uint32_t o[4];
#pragma unroll
  for (int m = 0; m < 4; m++) {
    const uint4 &ra = v[2 * m], &rb = v[2 * m + 1];
    const int k = i >> 1;
    const uint32_t xa = k == 0 ? ra.x : k == 1 ? ra.y : k == 2 ? ra.z : ra.w;
    const uint32_t xb = k == 0 ? rb.x : k == 1 ? rb.y : k == 2 ? rb.z : rb.w;
    o[m] = __byte_perm(xa, xb, (i & 1) ? 0x7632 : 0x5410);
  }
  return make_uint4(o[0], o[1], o[2], o[3]);
}

struct cpx { float r, i; };
__device__ __forceinline__ cpx cmul(cpx a, cpx b) { return {a.r * b.r - a.i * b.i, a.r * b.i + a.i * b.r}; }
__device__ __forceinline__ cpx csq(cpx a) { return {a.r * a.r - a.i * a.i, 2.f * (a.r * a.i)}; }
__device__ __forceinline__ cpx polar(float e, float t) {
  const float m = ex2(e);
  return {m * __cosf(t), m * __sinf(t)};
}
__device__ __forceinline__ float frac(float t) { return t - rintf(t); }

struct KgenRaw { uint32_t la, ai, cr, ci; unsigned short ldt; };
__device__ __forceinline__ void kgen_prep(KgenRaw r, int half, int lane, uint32_t tb, float& dt, float& k2048) {
  const float TWO_PI = 6.283185307179586f;
  dt = bf_round(expf(bf_lo(r.ldt)));
  float ks = 0.f;
  int m = half * 64 + 2 * lane;
#pragma unroll 1
  for (int j = 0; j < 2; j++, m++) {
    const float a2 = -(bf_round(expf(bf_lo(r.la))) * dt) * 1.4426950408889634f;
    const float f = frac((bf_lo(r.ai) * dt) * 0.15915494309189535f);
    const cpx w64 = polar(a2 * 64.f, frac(f * 64.f) * TWO_PI);
    const cpx we = polar(a2 * 2048.f, frac(f * 2048.f) * TWO_PI);
    ks += bf_lo(r.cr) * we.r - bf_lo(r.ci) * we.i;
    sts128(tb + T_PA + m * 16, fu(a2), fu(f * TWO_PI), fu(w64.r), fu(w64.i));
    sts64(tb + T_PB + m * 8, __byte_perm(r.cr, r.ci, 0x5410), fu(frac(f * 128.f) * TWO_PI));
    r.la >>= 16; r.ai >>= 16; r.cr >>= 16; r.ci >>= 16;
  }
#pragma unroll
  for (int o2 = 16; o2; o2 >>= 1) ks += __shfl_xor_sync(0xffffffffu, ks, o2);
  k2048 = ks;
}
__device__ __forceinline__ void kgen_round(int s0, int cnt, int lane, uint32_t tb, uint32_t open_bar, float (&k)[5][4]) {
  const int g = lane >> 2, c = lane & 3;
  const float pg = (float)g;
  const float n2 = (float)(2 + (g & 1)), m2 = (float)(g & 6), p2 = 128.f * n2 + m2;
  const float n3 = (float)(4 + (g & 3)), m3 = (float)(g & 4), p3 = 128.f * n3 + m3;
  const float n4 = (float)(8 + g), p4 = 128.f * n4;
  uint32_t pa = tb + T_PA + (8 * s0 + c) * 16, pb = tb + T_PB + (8 * s0 + c) * 8;
  uint4 qn[2] = {lds128(pa), lds128(pa + 64)};
  uint2 cn[2] = {lds64(pb), lds64(pb + 32)};
  uint32_t Q[6][14];
#pragma unroll 1
  for (int s = 0; s < cnt; s++) {
    const uint4 qq[2] = {qn[0], qn[1]};
    const uint2 cc[2] = {cn[0], cn[1]};
    pa += 128; pb += 64;
    qn[0] = lds128(pa); qn[1] = lds128(pa + 64);
    cn[0] = lds64(pb); cn[1] = lds64(pb + 32);
    uint32_t o[14];
#pragma unroll
    for (int h = 0; h < 2; h++) {
      const float a2 = uf(qq[h].x), f = uf(qq[h].y), f128 = uf(cc[h].y);
      const cpx w64 = {uf(qq[h].z), uf(qq[h].w)};
      const cpx C = {bf_lo(cc[h].x), bf_hi(cc[h].x)};
      const cpx d1 = polar(a2 * pg, f * pg);
      const cpx t2 = polar(a2 * p2, fmaf(f128, n2, f * m2));
      const cpx t3 = polar(a2 * p3, fmaf(f128, n3, f * m3));
      const cpx s8 = csq(csq(csq(d1)));
      const cpx t4 = polar(a2 * p4, f128 * n4);
      const cpx a0 = cmul(C, s8), a1 = cmul(a0, w64);
      const cpx t1 = cmul(d1, csq(w64));
      o[2 * h] = pack_bf(a0.r, -a0.i);
      o[2 * h + 1] = pack_bf(a1.r, -a1.i);
      o[4 + h] = pack_bf(d1.r, d1.i);
      o[6 + h] = pack_bf(t1.r, t1.i);
      o[8 + h] = pack_bf(t2.r, t2.i);
      o[10 + h] = pack_bf(t3.r, t3.i);
      o[12 + h] = pack_bf(t4.r, t4.i);
    }
#define KQ(i) case i: _Pragma("unroll") for (int e = 0; e < 14; e++) asm volatile("mov.b32 %0, %1;" : "=r"(Q[i][e]) : "r"(o[e])); break;
    switch (s) { KQ(0) KQ(1) KQ(2) KQ(3) KQ(4) default: KQ(5) }
#undef KQ
  }
  TS(40 + (s0 >> 2));
  mbar_wait(open_bar);
#pragma unroll
  for (int s = 0; s < 6; s++)
#pragma unroll
    for (int j = 0; j < 5; j++) mma_p(s < 4 || cnt > 4, k[j], Q[s][0], Q[s][1], Q[s][2], Q[s][3], Q[s][4 + 2 * j], Q[s][5 + 2 * j]);
}

__device__ __forceinline__ void build_tables(uint32_t tb, int lane, float (&k)[5][4], float k2048) {
  const int g = lane >> 2, c = lane & 3;
  const uint32_t kc = tb + T_KC + 16;
  {
    const uint32_t a0 = kc + 16 * g + 4 * c, a2 = kc + 2 * (256 + 4 * g + c);
    const uint32_t a3 = kc + 2 * (384 + 2 * g + 64 * (c & 1) + (c >> 1)), a4 = kc + 2 * (512 + g + 32 * c);
#pragma unroll
    for (int r = 0; r < 2; r++) {
      sts32(a0 + 128 * r, pack_bf(k[0][2 * r], k[0][2 * r + 1]));
      sts32(a0 + 128 * r + 256, pack_bf(k[1][2 * r], k[1][2 * r + 1]));
      const uint32_t w2 = pack_bf(k[2][2 * r], k[2][2 * r + 1]);
      const uint32_t w3 = pack_bf(k[3][2 * r], k[3][2 * r + 1]);
      const uint32_t w4 = pack_bf(k[4][2 * r], k[4][2 * r + 1]);
      sts16(a2 + 64 * r, w2); sts16(a2 + 64 * r + 128, w2 >> 16);
      sts16(a3 + 32 * r, w3); sts16(a3 + 32 * r + 64, w3 >> 16);
      sts16(a4 + 16 * r, w4); sts16(a4 + 16 * r + 32, w4 >> 16);
    }
  }
  if (lane == 0) { sts16(kc + 2 * 640, pack_bf(k2048, 0.f)); sts16(kc - 2, 0); }
  __syncwarp();
  const uint32_t td = tb + T_D + 32;
  {
    const uint4 v = lds128(kc + 16 * lane);
    const uint32_t pv = lds16(kc + 16 * lane - 2);
    sts128(td + 32 * lane, __byte_perm(v.x, pv, 0x5410), __byte_perm(v.x, v.x, 0x1032), __byte_perm(v.y, v.x, 0x7610),
           __byte_perm(v.y, v.y, 0x1032));
    sts128(td + 32 * lane + 16, __byte_perm(v.z, v.y, 0x7610), __byte_perm(v.z, v.z, 0x1032),
           __byte_perm(v.w, v.z, 0x7610), __byte_perm(v.w, v.w, 0x1032));
  }
  {
    const uint2 v = lds64(kc + 512 + 8 * lane);
    const uint32_t k4 = lds16(kc + 512 + 8 * lane + 8);
    const uint32_t pv = lds16(kc + (lane == 0 ? 510 : 512 + 8 * lane));
    const uint32_t k22 = __byte_perm(v.y, v.y, 0x1010);
    sts128(td + 1024 + 32 * lane, __byte_perm(v.x, pv, 0x5410), __byte_perm(v.x, v.x, 0x1010),
           __byte_perm(v.x, v.x, 0x1032), __byte_perm(v.y, v.x, 0x7610));
    sts128(td + 1024 + 32 * lane + 16, k22, k22, __byte_perm(v.y, v.y, 0x1032), __byte_perm(k4, v.y, 0x7610));
  }
  {
    const uint32_t kk = lds16(kc + 2 * 384);
    const uint32_t w = lane < 3 ? (kk | (kk << 16)) : (lane == 3 ? (kk << 16) : 0u);
    if (lane < 24) sts32(td + 4 * (lane < 16 ? 512 + lane : lane - 24), w);
    const uint32_t lo_ = lds16(kc + 2 * 511), le_ = lds16(kc + 2 * 512);
    const uint32_t ja = tb + T_5 + (lane < 16 ? 4 * lane : 256 + 4 * lane);
    sts32(ja, lane == 16 ? (le_ << 16) : 0u);
    sts32(ja + 384, lane == 16 ? (lo_ << 16) : 0u);
    sts32(tb + (lane < 16 ? T_7 : T_9 - 64) + 4 * lane, 0u);
  }
#pragma unroll
  for (int s = 0; s < 2; s++) {
    const uint32_t b = kc + 2 * (s ? 512 : 384) + 8 * lane;
    const uint2 v = lds64(b);
    uint32_t em = lds16(b - 2), e0 = v.x;
    const uint32_t e4 = lds16(b + 8);
    if (lane == 0) { em = 0; e0 = 0; }
    sts64(tb + (s ? T_7 : T_3) + 64 + 8 * lane, __byte_perm(v.x, em, 0x5432), __byte_perm(v.y, v.x, 0x7632));
    sts64(tb + (s ? T_9 : T_5) + 64 + 8 * lane, __byte_perm(v.y, e0, 0x5410), __byte_perm(e4, v.y, 0x5410));
  }
  __syncwarp();
}

__device__ __forceinline__ uint32_t box2w(int lo, int n, int o) {
  return ((unsigned)(o - lo) < (unsigned)n ? 0x3F80u : 0u) | ((unsigned)(o + 1 - lo) < (unsigned)n ? 0x3F800000u : 0u);
}

__device__ __forceinline__ void conv_channel(uint32_t ub, uint32_t tb, int lane, uint4* ydst) {
  const int g = lane >> 2, c = lane & 3, x = g - 2 * c;
  const uint32_t st = tb + T_ST + lane * 8;
  const int mi = lane >> 3;
  const uint32_t qa = ub + U_PAD + 16 * (lane & 7) + ((mi == 0 || mi == 3) ? U_ODD : 0) - (mi == 0 ? 16 : 0);
  const uint32_t kv = lds16(tb + T_KC + 16 + 2 * 512);
  {
    const uint32_t hb = ub + U_PAD + (mi & 1) * U_ODD + 16 * ((lane >> 4) + (lane & 7)) - 16;
    const int oh = c < 2 ? 8 + 2 * c : 2 * c - 8;
    const uint32_t bx0 = box2w(g - 4, 9, 2 * c), bx1 = box2w(g - 3, 7, 2 * c), bx2 = box2w(g - 4, 9, oh), bx3 = box2w(g - 3, 7, oh);
    uint32_t f7[9], f9a[9], f9b[9];
    const uint32_t fa = tb + T_7 + 4 * (8 + x);
#pragma unroll
    for (int m = 0; m < 9; m++) {
      f7[m] = lds32(fa + 32 * m);
      f9b[m] = lds32(fa + 320 + 32 * m);
      f9a[m] = lds32(fa + 316 + 32 * m);
    }
    TS(36);
    uint32_t z09[8], z07[8], zm9[8], zm7[8];
#pragma unroll
    for (int i = 0; i < 8; i++) {
      uint32_t h[4];
      ldsm4(h, hb + 128 * i);
      float y0, y1, y2, y3, w0, w1, w2, w3;
      mma0(y0, y1, y2, y3, bx0, bx1, bx2, bx3, h[2], c < 2 ? h[3] : h[1]);
      mma0(w0, w1, w2, w3, bx0, bx1, bx2, bx3, h[1], c < 2 ? h[2] : h[0]);
      z09[i] = pack_bf(y0, y1); z07[i] = pack_bf(y2, y3);
      zm9[i] = pack_bf(w0, w1); zm7[i] = pack_bf(w2, w3);
    }
    float a[4][2][4];
#pragma unroll
    for (int kap = 0; kap < 4; kap++)
#pragma unroll
      for (int sg = 0; sg < 2; sg++)
#pragma unroll
        for (int bk = 3; bk >= kap; bk--) {
          const int m = 2 * (bk - kap) + 1;
          float(&a0)[4] = a[bk][0];
          float(&a1)[4] = a[bk][1];
          if (sg == 0 && kap == 0) {
            mma0(a0[0], a0[1], a0[2], a0[3], f9a[m], f9a[m + 1], f9a[m - 1], f9a[m], z09[0], z09[1]);
            mma0(a1[0], a1[1], a1[2], a1[3], f9b[m], f9b[m + 1], f9b[m - 1], f9b[m], zm9[0], zm9[1]);
          } else if (sg == 0) {
            mma(a0[0], a0[1], a0[2], a0[3], f9a[m], f9a[m + 1], f9a[m - 1], f9a[m], z09[2 * kap], z09[2 * kap + 1]);
            mma(a1[0], a1[1], a1[2], a1[3], f9b[m], f9b[m + 1], f9b[m - 1], f9b[m], zm9[2 * kap], zm9[2 * kap + 1]);
          } else {
            mma(a0[0], a0[1], a0[2], a0[3], f7[m], f7[m + 1], f7[m - 1], f7[m], zm7[2 * kap], zm7[2 * kap + 1]);
            mma(a1[0], a1[1], a1[2], a1[3], f7[m], f7[m + 1], f7[m - 1], f7[m], z07[2 * kap], z07[2 * kap + 1]);
          }
        }
#pragma unroll
    for (int bk = 0; bk < 4; bk++) {
      sts64(st + 256 * (8 + 2 * bk), pack_bf(a[bk][0][0], a[bk][0][1]), pack_bf(a[bk][1][0], a[bk][1][1]));
      sts64(st + 256 * (9 + 2 * bk), pack_bf(a[bk][0][2], a[bk][0][3]), pack_bf(a[bk][1][2], a[bk][1][3]));
    }
  }
  TS(44);
  {
    const int oh = c < 3 ? 2 * c : -10;
    const uint32_t bx0 = box2w(g - 10, 5, 2 * c - 8), bx1 = box2w(g - 5, 3, 2 * c - 8), bx2 = box2w(g - 10, 5, oh), bx3 = box2w(g - 5, 3, oh);
    const uint32_t lb0 = ((unsigned)(x + 5) < 2u ? kv : 0u) | ((unsigned)(x + 4) < 2u ? kv << 16 : 0u);
    const uint32_t lb1 = ((unsigned)(x - 3) < 2u ? kv : 0u) | ((unsigned)(x - 4) < 2u ? kv << 16 : 0u);
    const int q0 = g - 1, q1 = c < 3 ? g : g - 2;
    uint32_t y0a = ub + U_PAD + (q0 & 1) * U_ODD + 16 * (q0 >> 1) + 4 * c;
    uint32_t y1a = ub + U_PAD + (q1 & 1) * U_ODD + 16 * (q1 >> 1) + 4 * c;
    uint2 a5[10], a3[10];
    const uint32_t aa = tb + T_5 + 4 * (8 + 2 * g - 2 * c);
#pragma unroll
    for (int m = 0; m < 10; m++) { a5[m] = lds64(aa + 32 * m); a3[m] = lds64(aa + 384 + 32 * m); }
    float T[6][4];
#pragma unroll
    for (int i = 0; i < 6; i++) T[i][0] = T[i][1] = T[i][2] = T[i][3] = 0.f;
    uint32_t x5[2] = {0, 0}, x3[2] = {0, 0}, yb[4], lq[4];
    uint32_t lqa = qa, sta = st + 256 * 8;
    uint2 sv;
    auto fetch = [&]() {
      yb[0] = lds32(y0a); yb[1] = lds32(y1a); yb[2] = lds32(y0a + 64); yb[3] = lds32(y1a + 64);
      ldsm4(lq, lqa);
      sv = lds64(min(sta, st + 256 * 15));
      y0a += 128; y1a += 128; lqa += 128; sta += 256;
    };
    fetch();
#pragma unroll 2
    for (int kap = -1; kap < 13; kap++) {
      float yn[2][4];
      mma0(yn[0][0], yn[0][1], yn[0][2], yn[0][3], bx0, bx1, bx2, bx3, yb[0], yb[1]);
      mma0(yn[1][0], yn[1][1], yn[1][2], yn[1][3], bx0, bx1, bx2, bx3, yb[2], yb[3]);
      sts64_p(kap > 0, sta - 256 * 7, pack_bf(T[0][0], T[0][1]), pack_bf(T[0][2], T[0][3]));
#pragma unroll
      for (int i = 0; i < 5; i++)
        mmac_p((unsigned)kap < 12u - i, T[i], a5[2 * i + 1].x, a5[2 * i + 1].y, a5[2 * i].x, a5[2 * i].y, x5[0], x5[1], T[i + 1]);
      const float ci[4] = {bf_lo(sv.x), bf_hi(sv.x), bf_lo(sv.y), bf_hi(sv.y)};
      mmac_p(kap < 7, T[5], lq[0], lq[1], lq[2], lq[3], lb0, lb1, ci);
      fetch();
#pragma unroll
      for (int i = 0; i < 5; i++)
        mma_p((unsigned)kap < 12u - i, T[i], a3[2 * i + 1].x, a3[2 * i + 1].y, a3[2 * i].x, a3[2 * i].y, x3[0], x3[1]);
#pragma unroll
      for (int hh = 0; hh < 2; hh++) { x5[hh] = pack_bf(yn[hh][0], yn[hh][1]); x3[hh] = pack_bf(yn[hh][2], yn[hh][3]); }
    }
  }
  TS(45);
  {
    uint32_t F[66];
    const uint32_t fa = tb + T_D + 32 + 4 * x;
#pragma unroll
    for (int m = 0; m < 66; m++) F[m] = lds32(fa + 32 * m);
    float T[5][4];
#pragma unroll
    for (int i = 0; i < 5; i++) T[i][0] = T[i][1] = T[i][2] = T[i][3] = 0.f;
    uint32_t qd[8][4], held[2] = {0, 0};
    uint32_t qp = qa + 128 * 15, sta = st + 256 * 14;
    uint4* yd = ydst + 19 * 16;
#pragma unroll
    for (int i = 0; i < 6; i++) ldsm4(qd[i], qp - 16 * i);
    uint2 sv = lds64(sta + 256);
    float ci[4] = {bf_lo(sv.x), bf_hi(sv.x), bf_lo(sv.y), bf_hi(sv.y)};
    TS(46);
#pragma unroll 1
    for (int be = 15; be >= 0; be--) {
#pragma unroll
      for (int k = 4; k >= 1; k--)
        mmac_p(be <= 15 - k, T[k], qd[0][0], qd[0][1], qd[0][2], qd[0][3], F[16 * k + 1], F[16 * k], T[k - 1]);
      mmac(T[0], qd[0][0], qd[0][1], qd[0][2], qd[0][3], F[1], F[0], ci);
      ldsm4(qd[6], qp - 16 * 6);
      ldsm4(qd[7], qp - 16 * 7);
      sv = lds64(sta);
#pragma unroll
      for (int i = 1; i < 8; i++) {
#pragma unroll
        for (int k = 3; k >= 0; k--)
          mma_p(k == 0 || be <= 15 - k, T[k], qd[i][0], qd[i][1], qd[i][2], qd[i][3], F[16 * k + 2 * i + 1], F[16 * k + 2 * i]);
        if (i < 7) ldsm4(qd[i - 1], qp - 128 - 16 * (i - 1));
        if (i == 2) {
          const uint32_t w0 = pack_bf(T[4][0], T[4][1]), w1 = pack_bf(T[4][2], T[4][3]);
          st_x_p(be <= 10 && !(be & 1), yd, nz(w0), w1, held[0], held[1]);
          held[0] = w0; held[1] = w1;
        }
        if (i == 4) {
          if (be <= 4) sv = make_uint2(0, 0);
          ci[0] = bf_lo(sv.x); ci[1] = bf_hi(sv.x); ci[2] = bf_lo(sv.y); ci[3] = bf_hi(sv.y);
        }
      }
      qp -= 128; sta -= 256; yd -= 16;
    }
#pragma unroll
    for (int B = 1; B >= 0; B--)
      st_x(ydst + B * 32, nz(pack_bf(T[2 * B][0], T[2 * B][1])), pack_bf(T[2 * B][2], T[2 * B][3]),
           pack_bf(T[2 * B + 1][0], T[2 * B + 1][1]), pack_bf(T[2 * B + 1][2], T[2 * B + 1][3]));
  }
}

__device__ __forceinline__ void feat(const float (&acc)[48], int j0, const uint32_t (&wf)[4], uint32_t* w) {
  const uint32_t a0 = pack_bf(acc[4 * j0], acc[4 * j0 + 1]), a1 = pack_bf(acc[4 * j0 + 2], acc[4 * j0 + 3]);
  const uint32_t a2 = pack_bf(acc[4 * j0 + 4], acc[4 * j0 + 5]), a3 = pack_bf(acc[4 * j0 + 6], acc[4 * j0 + 7]);
  float p[8];
  mma0(p[0], p[1], p[2], p[3], a0, a1, a2, a3, wf[0], wf[1]);
  mma0(p[4], p[5], p[6], p[7], a0, a1, a2, a3, wf[2], wf[3]);
  w[0] = pack_bf(p[0], p[2]); w[1] = pack_bf(p[1], p[3]); w[2] = pack_bf(p[4], p[6]); w[3] = pack_bf(p[5], p[7]);
}
__device__ __forceinline__ void dual_softmax(const uint32_t* w, uint32_t* e) {
  const float L = 1.44268798828125f;
  uint32_t mx = bmax2(bmax2(w[0], w[1]), bmax2(w[2], w[3]));
  uint32_t mn = bmin2(bmin2(w[0], w[1]), bmin2(w[2], w[3]));
  mx = bmax2(mx, __shfl_xor_sync(0xffffffffu, mx, 1));
  mn = bmin2(mn, __shfl_xor_sync(0xffffffffu, mn, 1));
  mx = bmax2(mx, __shfl_xor_sync(0xffffffffu, mx, 2));
  mn = bmin2(mn, __shfl_xor_sync(0xffffffffu, mn, 2));
  const float mx0 = bf_lo(mx) * -L, mx1 = bf_hi(mx) * -L, mn0 = bf_lo(mn) * L, mn1 = bf_hi(mn) * L;
  float ep[2][4], em[2][4];
#pragma unroll
  for (int i = 0; i < 4; i++) {
    const float x0 = bf_lo(w[i]), x1 = bf_hi(w[i]);
    ep[0][i] = ex2(fmaf(x0, L, mx0)); em[0][i] = ex2(fmaf(x0, -L, mn0));
    ep[1][i] = ex2(fmaf(x1, L, mx1)); em[1][i] = ex2(fmaf(x1, -L, mn1));
  }
  __half2 sp = __floats2half2_rn((ep[0][0] + ep[0][1]) + (ep[0][2] + ep[0][3]), (ep[1][0] + ep[1][1]) + (ep[1][2] + ep[1][3]));
  __half2 sm = __floats2half2_rn((em[0][0] + em[0][1]) + (em[0][2] + em[0][3]), (em[1][0] + em[1][1]) + (em[1][2] + em[1][3]));
  sp = __hadd2(sp, __shfl_xor_sync(0xffffffffu, sp, 1));
  sm = __hadd2(sm, __shfl_xor_sync(0xffffffffu, sm, 1));
  sp = __hadd2(sp, __shfl_xor_sync(0xffffffffu, sp, 2));
  sm = __hadd2(sm, __shfl_xor_sync(0xffffffffu, sm, 2));
  const float rp[2] = {rcp(__low2float(sp)), rcp(__high2float(sp))}, rm[2] = {rcp(__low2float(sm)), rcp(__high2float(sm))};
#pragma unroll
  for (int i = 0; i < 4; i++) {
    const int r = i & 1, k = i & 2;
    e[i] = pack_bf(ep[r][k] * rp[r], ep[r][k + 1] * rp[r]);
    e[4 + i] = pack_bf(em[r][k] * rm[r], em[r][k + 1] * rm[r]);
  }
}

__global__ void __launch_bounds__(NTHREADS, 1)
fused_kernel(const __grid_constant__ CUtensorMap mx, const __grid_constant__ CUtensorMap mw,
             const __grid_constant__ CUtensorMap mo, const __grid_constant__ CUtensorMap mu,
             const __grid_constant__ CUtensorMap mout, const Params P) {
  constexpr uint32_t sb = SB;
  const int tid = threadIdx.x, lane = tid & 31;
  const int warp = __shfl_sync(0xffffffffu, tid >> 5, 0);
  const int b = blockIdx.x, oct = b >> 3, i8 = b & 7;
  const int rt = oct < 8 ? oct : 15 - oct;
  const int hp = (oct >> 3) * 8 + i8;

  if (warp >= 12) asm volatile("setmaxnreg.dec.sync.aligned.u32 32;");
  if (warp == 12) {
    if (lane == 0) {
      asm volatile("prefetch.tensormap [%0];" ::"l"(&mw) : "memory");
      asm volatile("prefetch.tensormap [%0];" ::"l"(&mx) : "memory");
#pragma unroll
      for (int i = 0; i < 8; i++) mbar_init(BAR(MB_FULL + i), 1);
      asm volatile("fence.mbarrier_init.release.cluster;" ::: "memory");
    }
    __syncwarp();
    if (lane < 8) mbar_expect(BAR(MB_FULL) + 8 * lane, lane < 7 ? 28672 : 29696);
    __syncwarp();
    nb_arrive(NB_RDY, 256);
#pragma unroll 1
    for (int kb = 0; kb < 8; kb++) {
      e_tma3d(sb + OFF_W + kb * 12288, &mw, BAR(MB_FULL) + 8 * kb, hp * 32, kb * 64, 0);
      if (kb < 4) e_tma2d(sb + OFF_X + kb * 16384, &mx, BAR(MB_FULL) + 8 * kb, kb * 64, rt * 256);
      if (kb == 3) e_prefetch(P.x + (size_t)(rt * 256 + hp * 8) * 512, 8192);
    }
    e_bulk(sb + OFF_PHI, P.wphi + hp * 512, 1024, BAR(MB_FULL + 7));
    if (smem_u32(smem_raw) != SB) __trap();
  }
  if (warp >= 12) {
    if (warp == 12) {
      nb_sync(NB_PROD, 64);
#pragma unroll 1
      for (int n = 0; n < 12; n++) {
        mbar_wait(BAR(MB_EMPTY) + 8 * n);
        const int m = n + 4;
        e_tma2d(sb + OFF_X + (n & 3) * 16384, &mx, BAR(MB_FULL) + 8 * m, (m & 7) * 64, rt * 256 + (m >> 3) * 128);
        if (n == STEP_PF) e_prefetch(P.x + (size_t)(rt * 256 + 128 + hp * 8) * 512, 8192);
        if (n == STEP_U) e_tma5d(sb + OFF_U, &mu, BAR(MB_URAW), i8 * 64, oct * 4);
        if (n == 7) e_prefetch(P.wo + (size_t)b * 2048, 4096);
      }
#pragma unroll 1
      for (int i = 0; i < 8; i++) {
        mbar_wait(BAR(MB_EMPTY + 11) + 8 * ((0x43221000u >> (4 * i)) & 7));
        const int w0 = (0x54736210u >> (4 * i)) & 7;
        const int col = (hp & 3) * 128 + (w0 >> 2) * 64;
        e_tma2d(sb + OFF_W + w0 * 16384, &mo, BAR(MB_WO) + 8 * (w0 >> 2), col, w0 * 64);
        e_tma2d(sb + OFF_W + w0 * 16384 + 8192, &mo, BAR(MB_WO) + 8 * (w0 >> 2), col ^ 64, w0 * 64);
      }
    } else {
      if (warp == 13) {
        if (lane == 0) {
#pragma unroll
          for (int i = 8; i < 38; i++) mbar_init(BAR(i), i < MB_EMPTY ? 1 : (i < MB_CLOSE ? 4 : 12));
          asm volatile("fence.mbarrier_init.release.cluster;" ::: "memory");
        }
        __syncwarp();
        if (lane < 11) mbar_expect(BAR(MB_FULL + 8) + 8 * lane, lane < 9 ? 16384 : 65536);
        __syncwarp();
        nb_arrive(NB_PROD, 64);
        nb_arrive(NB_PREP, 288);
      }
      nb_sync(NB_RDY, 256);
      const unsigned cnt0 = ld_x32(&g_cnt);
      uint4* po = g_o + (size_t)(rt * 4 * 32 + hp * 2) * 128;
      uint4* py = g_y + (size_t)b * 1024;
      uint4* pp = g_part + (size_t)(hp * 8 + rt) * 144;
#pragma unroll 1
      for (int i = tid - 416; i < 1024; i += 96) {
        st_x(po + (i >> 8) * 4096 + (i & 255), 0, 0, 0, 0);
        st_x(py + i, 0, 0, 0, 0);
        if (i < 144) st_x(pp + i, 0, 0, 0, 0);
      }
      if (tid == 416) TS1(48);
      mbar_wait(BAR(MB_URAW));
      uint4* dst = g_uT + (size_t)(i8 * 64 + (lane >> 2)) * 256 + (lane & 1) * 128 + oct * 8 + ((lane >> 1) & 1);
#pragma unroll 1
      for (int i = warp - 13; i < 32; i += 3) {
        uint32_t r[4];
        ldsm4t(r, sb + OFF_U + (i >> 3) * 4096 + lane * 128 + (((i ^ lane) & 7) << 4));
        dst[(i & 7) * 2048 + (i >> 3) * 2] = make_uint4(r[0], r[1], r[2], r[3]);
      }
      asm volatile("fence.proxy.async;" ::: "memory");
      nb_sync(NB_INIT, 96);
      if (warp == 13) {
        if (tid == 416) TS1(49);
        sts128(sb + OFF_U + (lane >> 4) * U_CH + ((lane >> 3) & 1) * U_ODD + (lane & 7) * 16, 0, 0, 0, 0);
        sts128(sb + OFF_U + (2 + (lane >> 4)) * U_CH + ((lane >> 3) & 1) * U_ODD + (lane & 7) * 16, 0, 0, 0, 0);
        if (lane == 0) asm volatile("red.release.gpu.global.add.u32 [%0], 1;" ::"l"(&g_cnt) : "memory");
        if (tid == 416) TS1(50);
#pragma unroll 1
        for (int i = 0; i < SPIN_MAX; i++) {
          unsigned v;
          asm volatile("ld.acquire.gpu.global.u32 %0, [%1];" : "=r"(v) : "l"(&g_cnt) : "memory");
          if ((int)(v - ((cnt0 & ~(unsigned)(NCTA - 1)) + NCTA)) >= 0) break;
        }
        asm volatile("fence.proxy.async;" ::: "memory");
        __syncwarp();
        if (tid == 416) TS1(51);
        e_expect(BAR(MB_UFULL), 16384);
#pragma unroll 1
        for (int i = 0; i < 8; i++)
          e_bulk(sb + OFF_U + (i >> 1) * U_CH + (i & 1) * U_ODD + U_PAD, g_uT + (size_t)(b * 8 + i) * 128, 2048, BAR(MB_UFULL));
      }
    }
    return;
  }

  asm volatile("setmaxnreg.inc.sync.aligned.u32 160;");
  const int wg = warp >> 2, w = warp & 3, t = tid & 127;
  const int g = lane >> 2, c = lane & 3;
  const uint32_t tb = sb + OFF_T + w * T_CH;
  const int d = b * 4 + w;
  if (wg != 0) {
    KgenRaw raw;
    const int o = d * 64 + (wg & 1) * 32 + lane;
    raw.la = __ldg((const uint32_t*)P.logA + o); raw.ai = __ldg((const uint32_t*)P.Aim + o);
    raw.cr = __ldg((const uint32_t*)P.Cre + o); raw.ci = __ldg((const uint32_t*)P.Cim + o);
    raw.ldt = __ldg((const unsigned short*)P.logdt + d);
    const unsigned short dsk = __ldg((const unsigned short*)P.Dskip + d);
    float k[5][4], dt, k2048;
    kgen_prep(raw, wg & 1, lane, tb, dt, k2048);
    nb_sync(NB_PREP, 288);
    TS(wg * 16 + 1);
#pragma unroll
    for (int j = 0; j < 5; j++) k[j][0] = k[j][1] = k[j][2] = k[j][3] = 0.f;
#pragma unroll 1
    for (int r = 0; r < wg; r++) {
      kgen_round(r ? 12 : (wg - 1) * 6, r ? 4 : 6, lane, tb, BAR(MB_EMPTY + 7) + 64 * r, k);
      if (r == 0 && lane == 0 && (fu(k[0][0]) & fu(k[1][0]) & fu(k[2][0]) & fu(k[3][0]) & fu(k[4][0])) != 0xffffffffu)
        mbar_arrive(BAR(MB_CLOSE));
    }
    if (wg == 2) {
      TS(34);
      nb_sync(NB_KPART, 256);
      const float sc = 2.f * dt;
#pragma unroll
      for (int j = 0; j < 5; j++) {
        const uint4 v = lds128(tb + j * 512 + lane * 16);
        k[j][0] = (k[j][0] + uf(v.x)) * sc; k[j][1] = (k[j][1] + uf(v.y)) * sc;
        k[j][2] = (k[j][2] + uf(v.z)) * sc; k[j][3] = (k[j][3] + uf(v.w)) * sc;
      }
      k2048 = (k2048 + uf(lds32(tb + 2560))) * sc;
      if (lane == 0) k[0][0] += bf_lo(dsk);
      __syncwarp();
      build_tables(tb, lane, k, k2048);
      TS(35);
      mbar_wait(BAR(MB_UFULL));
      conv_channel(sb + OFF_U + w * U_CH, tb, lane, g_y + (size_t)d * 256 + lane);
      if (lane == 0) mbar_arrive(BAR(MB_BDONE));
      TS(37);
      const int lam = w * 8 + g;
      const uint4* src = g_y + (size_t)(oct * 32 + c * 8) * 256 + i8 * 32 + lam;
      uint4 v[8];
#pragma unroll 1
      for (int it = 0; it < SPIN_MAX; it++) {
        uint32_t m = 0xffffffffu;
#pragma unroll
        for (int i = 0; i < 8; i++) v[i] = ld_x(src + i * 256);
#pragma unroll
        for (int i = 0; i < 8; i++) m = min(m, v[i].x);
        if (__all_sync(0xffffffffu, m != 0)) break;
      }
      __nv_bfloat16* dst = P.out + (size_t)(i8 * 256 + (lam >> 2) * 16 + (lam & 3) * 2) * 1024 + 512 + oct * 32 + c * 8;
#pragma unroll
      for (int i = 0; i < 8; i++) *(uint4*)(dst + (size_t)((i >> 2) * 128 + ((i >> 1) & 1) * 8 + (i & 1)) * 1024) = tr_row(v, i);
      TS(38);
      GT(63);
      return;
    }
#pragma unroll
    for (int j = 0; j < 5; j++) sts128(tb + j * 512 + lane * 16, fu(k[j][0]), fu(k[j][1]), fu(k[j][2]), fu(k[j][3]));
    if (lane == 0) sts32(tb + 2560, fu(k2048));
    nb_arrive(NB_KPART, 256);
    mbar_wait(BAR(MB_CLOSE));
    TS(30);
  } else {
    nb_sync(NB_RDY, 256);
    TS(0);
  }

  float acc[2][48];
  {
    uint32_t fb = BAR(MB_FULL) + 64 * wg;
    uint32_t da = (uint32_t)mkdesc(sb + OFF_X, 16, 0, 0), db = (uint32_t)mkdesc(sb + OFF_W, 4096, 0, 0);
    constexpr uint64_t ha = mkdesc(0, 0, 1024, 1), hb = mkdesc(0, 0, 512, 2);
#pragma unroll 1
    for (int kb = 0; kb < 8; kb++) {
      mbar_wait(fb);
      if (kb == 0) TS(wg * 16 + 2);
      WG_FENCE();
#pragma unroll
      for (int k = 0; k < 4; k++) {
        wgmma_ss_n96(acc[0], ha | (da + 2 * k), hb | (db + 64 * k), k ? 1 : kb);
        wgmma_ss_n96(acc[1], ha | (da + 2 * k + 512), hb | (db + 64 * k), k ? 1 : kb);
      }
      WG_COMMIT();
      WG_WAIT(1);
      if (kb > 0 && lane == 0) mbar_arrive(fb + 8 * (MB_EMPTY - MB_FULL - 1));
      fb += 8; db += 768;
      da = kb == 3 ? da - 3072 : da + 1024;
    }
    WG_WAIT(0);
    if (lane == 0) mbar_arrive(fb + 8 * (MB_EMPTY - MB_FULL - 1));
    mbar_wait(fb + 8 * (MB_EMPTY - MB_FULL - 1));
  }
  uint32_t wf[2][4];
  ldsm4t(wf[0], sb + OFF_PHI + (lane & 15) * 32 + (lane >> 4) * 16);
  ldsm4t(wf[1], sb + OFF_PHI + 512 + (lane & 15) * 32 + (lane >> 4) * 16);
  TS(wg * 16 + 3);

  uint32_t pw[32], eq[32];
#pragma unroll
  for (int u = 0; u < 4; u++)
#pragma unroll
    for (int h = 0; h < 2; h++) feat(acc[u & 1], (u < 2 ? 4 : 0) + 2 * h, wf[h], pw + 8 * u + 4 * h);
  {
    uint32_t all = 0xffffffffu;
#pragma unroll
    for (int i = 0; i < 16; i++) all &= pw[2 * i];
    if (wg == 0 && lane == 0 && all != 0xffffffffu) mbar_arrive(BAR(MB_CLOSE));
  }
  const uint32_t stg0 = sb + OFF_STG0, stg1 = sb + OFF_X + 32768;
  uint32_t sl = (wg ? stg1 : stg0) + w * 3072 + lane * 16;
#pragma unroll
  for (int mt = 0; mt < 2; mt++)
#pragma unroll
    for (int h = 0; h < 2; h++) {
      const float* a = acc[mt] + 32 + 8 * h;
      stsm4(sl + mt * 12288 + 2048 + h * 512, pack_bf(a[0], a[1]), pack_bf(a[2], a[3]), pack_bf(a[4], a[5]), pack_bf(a[6], a[7]));
    }
#pragma unroll 1
  for (int u = 0; u < 4; u++) {
#pragma unroll
    for (int i = 0; i < 16; i++) eq[i] = eq[16 + i];
    dual_softmax(pw, eq + 16);
    dual_softmax(pw + 4, eq + 24);
    if (u < 2) {
#pragma unroll
      for (int i = 0; i < 4; i++) stsm4(sl + i * 512, eq[16 + 4 * i], eq[17 + 4 * i], eq[18 + 4 * i], eq[19 + 4 * i]);
      if (wg) nb_arrive(NB_ST0 + u, 256);
      sl += 12288;
    }
#pragma unroll
    for (int i = 0; i < 24; i++) pw[i] = pw[i + 8];
  }
  TS(wg * 16 + 4);
  const uint32_t kvs = stg0;
  if (wg == 0) {
    nb_sync(NB_WG0, 128);
    mbar_wait(BAR(MB_UFULL));
    mbar_wait(BAR(MB_EMPTY + 15));
    float kv[12];
#pragma unroll
    for (int i = 0; i < 12; i++) kv[i] = 0.f;
    const int mi = lane >> 3;
    const uint32_t ao = w * 512 + (lane & 7) * 16 + ((mi & 1) * 2 + (mi >> 1)) * 128, bo = 2048 + (w >> 1) * 512 + lane * 16;
#pragma unroll 1
    for (int j = 0; j < 4; j++) {
      if (j >= 2) nb_sync(NB_ST0 + j - 2, 256);
      const uint32_t sg = (j >= 2 ? stg1 : stg0) + (j & 1) * 12288;
      uint32_t a[4][4], bb[4][4];
#pragma unroll
      for (int s = 0; s < 4; s++) { ldsm4t(a[s], sg + s * 3072 + ao); ldsm4t(bb[s], sg + s * 3072 + bo); }
#pragma unroll
      for (int s = 0; s < 4; s++) {
        mma(kv[0], kv[1], kv[2], kv[3], a[s][0], a[s][1], a[s][2], a[s][3], bb[s][0], bb[s][1]);
        mma(kv[4], kv[5], kv[6], kv[7], a[s][0], a[s][1], a[s][2], a[s][3], bb[s][2], bb[s][3]);
        mma(kv[8], kv[9], kv[10], kv[11], a[s][0], a[s][1], a[s][2], a[s][3], 0x3F803F80u, 0x3F803F80u);
      }
    }
    uint4* pp = g_part + (size_t)(hp * 8 + rt) * 144;
    st_x(pp + t, nz(pack_bf(kv[0], kv[1])), pack_bf(kv[2], kv[3]), pack_bf(kv[4], kv[5]), pack_bf(kv[6], kv[7]));
    if (c < 2) st_x32((uint32_t*)(pp + 128) + w * 16 + c * 8 + g, nz(fu(c ? kv[10] : kv[8])));
    TS(5);
    const uint4* ps = g_part + (size_t)hp * 8 * 144 + t;
    const uint32_t* zs = (const uint32_t*)(g_part + (size_t)(hp * 8 + (lane >> 4) * 4) * 144 + 128) + w * 16 + (lane & 15);
    uint4 v[8];
    uint32_t zv[4];
#pragma unroll 1
    for (int it = 0; it < SPIN_MAX; it++) {
#pragma unroll
      for (int i = 0; i < 8; i++) v[i] = ld_x(ps + i * 144);
#pragma unroll
      for (int i = 0; i < 4; i++) zv[i] = ld_x32(zs + i * 576);
      uint32_t m = min(min(zv[0], zv[1]), min(zv[2], zv[3]));
#pragma unroll
      for (int i = 0; i < 8; i++) m = min(m, v[i].x);
      if (__all_sync(0xffffffffu, m != 0)) break;
    }
    float s4[4][4];
#pragma unroll
    for (int i = 0; i < 4; i++) s4[i][0] = s4[i][1] = s4[i][2] = s4[i][3] = 0.f;
    const uint32_t eye = (g >> 1) == c ? ((g & 1) ? 0x3F800000u : 0x3F80u) : 0u;
#pragma unroll
    for (int r = 0; r < 8; r++) {
      mma_k8(s4[(r & 1) * 2], v[r].x, v[r].y, eye);
      mma_k8(s4[(r & 1) * 2 + 1], v[r].z, v[r].w, eye);
    }
    float s[8];
#pragma unroll
    for (int i = 0; i < 8; i++) s[i] = s4[i >> 2][i & 3] + s4[2 + (i >> 2)][i & 3];
    float zsum = (uf(zv[0]) + uf(zv[1])) + (uf(zv[2]) + uf(zv[3]));
    zsum += __shfl_xor_sync(0xffffffffu, zsum, 16);
    stsm4(kvs + w * 512 + lane * 16, pack_bf(s[0], s[1]), pack_bf(s[2], s[3]), pack_bf(s[4], s[5]), pack_bf(s[6], s[7]));
    if (lane < 16) sts16(kvs + 2048 + (w * 16 + lane) * 2, pack_bf(zsum, 0.f));
    TS(6);
  }
  nb_sync(NB_KV, 256);
  {
    uint32_t kb_[4][4], zb[8];
#pragma unroll
    for (int i = 0; i < 4; i++) ldsm4t(kb_[i], kvs + i * 512 + lane * 16);
#pragma unroll
    for (int i = 0; i < 8; i++) zb[i] = lds32(kvs + 2048 + i * 16 + c * 4);
    uint4* od = g_o + (size_t)((rt * 4 + wg * 2) * 32 + hp * 2) * 128 + t;
#pragma unroll 1
    for (int mt = 0; mt < 2; mt++) {
#pragma unroll
      for (int h = 0; h < 2; h++) {
        const uint32_t* e = eq + 8 * h;
        float n[8], dn[4];
        mma0(dn[0], dn[1], dn[2], dn[3], e[0], e[1], e[2], e[3], zb[4 * h], zb[4 * h + 1]);
        mma0(n[0], n[1], n[2], n[3], e[0], e[1], e[2], e[3], kb_[2 * h][0], kb_[2 * h][1]);
        mma0(n[4], n[5], n[6], n[7], e[0], e[1], e[2], e[3], kb_[2 * h][2], kb_[2 * h][3]);
        mma(dn[0], dn[1], dn[2], dn[3], e[4], e[5], e[6], e[7], zb[4 * h + 2], zb[4 * h + 3]);
        mma(n[0], n[1], n[2], n[3], e[4], e[5], e[6], e[7], kb_[2 * h + 1][0], kb_[2 * h + 1][1]);
        mma(n[4], n[5], n[6], n[7], e[4], e[5], e[6], e[7], kb_[2 * h + 1][2], kb_[2 * h + 1][3]);
        const float r0 = rcp(dn[0] + 1e-6f), r1 = rcp(dn[2] + 1e-6f);
        st_x(od + h * 128, nz(pack_bf(n[0] * r0, n[1] * r0)), pack_bf(n[2] * r1, n[3] * r1), pack_bf(n[4] * r0, n[5] * r0),
             pack_bf(n[6] * r1, n[7] * r1));
      }
#pragma unroll
      for (int i = 0; i < 16; i++) eq[i] = eq[16 + i];
      od += 4096;
    }
  }
  TS(wg * 16 + 7);
  const int rb = rt * 4 + (hp >> 2);
  const uint4* osrc = g_o + (size_t)(rb * 32 + wg * 16) * 128 + t;
  uint4 af[16];
  {
    const uint32_t* probe = (const uint32_t*)(osrc - lane + (lane & 15) * 128 + (lane >> 4) * 31);
#pragma unroll 1
    for (int it = 0; it < SPIN_MAX; it++) {
      uint32_t m = ld_x32(probe);
#pragma unroll
      for (int i = 0; i < 4; i++) af[i] = ld_x(osrc + i * 128);
#pragma unroll
      for (int i = 0; i < 4; i++) m = min(m, af[i].x);
      if (__all_sync(0xffffffffu, m != 0)) break;
    }
  }
#pragma unroll
  for (int i = 4; i < 16; i++) af[i] = ld_x(osrc + i * 128);
  TS(wg * 16 + 8);
  mbar_wait(BAR(MB_WO) + 8 * wg);
  mbar_wait(BAR(MB_BDONE));
  TS(wg * 16 + 9);
  float oc[64];
  {
    const uint64_t db = mkdesc(sb + OFF_W, 8192, 1024, 1) + wg * 4096;
#pragma unroll
    for (int j = 0; j < 4; j++) {
      if (j) {
#pragma unroll 1
        for (int it = 0; it < SPIN_MAX; it++) {
          const uint32_t m = min(min(af[4 * j].x, af[4 * j + 1].x), min(af[4 * j + 2].x, af[4 * j + 3].x));
          if (__all_sync(0xffffffffu, m != 0)) break;
#pragma unroll
          for (int i = 0; i < 4; i++) af[4 * j + i] = ld_x(osrc + (4 * j + i) * 128);
        }
      }
      WG_FENCE();
#pragma unroll
      for (int k = 0; k < 4; k++) wgmma_rs_n128(oc, af[4 * j + k], db + 128 * k + 1024 * j, j | k);
    }
    WG_COMMIT();
    WG_WAIT(0);
  }
  TS(wg * 16 + 10);
  const uint32_t xo = stg1 + wg * 16384 + t * 16, xi = stg1 + (wg ^ 1) * 16384 + t * 16;
#pragma unroll
  for (int i = 0; i < 8; i++) sts128(xo + i * 2048, fu(oc[32 + 4 * i]), fu(oc[33 + 4 * i]), fu(oc[34 + 4 * i]), fu(oc[35 + 4 * i]));
  nb_sync(NB_RED, 256);
  const uint32_t ot = stg0 + warp * 2048;
#pragma unroll
  for (int i = 0; i < 8; i += 2) {
    const uint4 v0 = lds128(xi + i * 2048), v1 = lds128(xi + i * 2048 + 2048);
    stsm4(ot + (lane & 15) * 128 + (((i + (lane >> 4)) ^ (lane & 7)) << 4),
          pack_bf(oc[4 * i] + uf(v0.x), oc[4 * i + 1] + uf(v0.y)), pack_bf(oc[4 * i + 2] + uf(v0.z), oc[4 * i + 3] + uf(v0.w)),
          pack_bf(oc[4 * i + 4] + uf(v1.x), oc[4 * i + 5] + uf(v1.y)), pack_bf(oc[4 * i + 6] + uf(v1.z), oc[4 * i + 7] + uf(v1.w)));
  }
  asm volatile("fence.proxy.async.shared::cta;" ::: "memory");
  __syncwarp();
  e_store2d(&mout, ot, (hp & 3) * 128 + wg * 64, rb * 64 + w * 16);
  TS(wg * 16 + 11);
  GT(61 + wg);
}

typedef CUresult (*EncodeFn)(CUtensorMap*, CUtensorMapDataType, cuuint32_t, void*, const cuuint64_t*, const cuuint64_t*,
                             const cuuint32_t*, const cuuint32_t*, CUtensorMapInterleave, CUtensorMapSwizzle,
                             CUtensorMapL2promotion, CUtensorMapFloatOOBfill);

}

extern "C" void kernel_launch(void* const* d_in, const int* in_sizes, int n_in, void* d_out, int out_size) {
  (void)in_sizes; (void)n_in; (void)out_size;
  void* fn = nullptr;
  cudaDriverEntryPointQueryResult qr;
  cudaGetDriverEntryPoint("cuTensorMapEncodeTiled", &fn, cudaEnableDefault, &qr);
  EncodeFn enc = (EncodeFn)fn;
  CUtensorMap mx, mw, mo, mu, mout;
  const cuuint32_t es[5] = {1, 1, 1, 1, 1};
  {
    cuuint64_t dims[2] = {512, 2048}, st[1] = {1024};
    cuuint32_t box[2] = {64, 128};
    enc(&mx, CU_TENSOR_MAP_DATA_TYPE_BFLOAT16, 2, d_in[0], dims, st, box, es, CU_TENSOR_MAP_INTERLEAVE_NONE,
        CU_TENSOR_MAP_SWIZZLE_128B, CU_TENSOR_MAP_L2_PROMOTION_L2_128B, CU_TENSOR_MAP_FLOAT_OOB_FILL_NONE);
  }
  {
    cuuint64_t dims[3] = {512, 512, 3}, st[2] = {3072, 1024};
    cuuint32_t box[3] = {32, 64, 3};
    enc(&mw, CU_TENSOR_MAP_DATA_TYPE_BFLOAT16, 3, d_in[1], dims, st, box, es, CU_TENSOR_MAP_INTERLEAVE_NONE,
        CU_TENSOR_MAP_SWIZZLE_64B, CU_TENSOR_MAP_L2_PROMOTION_L2_128B, CU_TENSOR_MAP_FLOAT_OOB_FILL_NONE);
  }
  {
    cuuint64_t dims[2] = {512, 512}, st[1] = {1024};
    cuuint32_t box[2] = {64, 64};
    enc(&mo, CU_TENSOR_MAP_DATA_TYPE_BFLOAT16, 2, d_in[3], dims, st, box, es, CU_TENSOR_MAP_INTERLEAVE_NONE,
        CU_TENSOR_MAP_SWIZZLE_128B, CU_TENSOR_MAP_L2_PROMOTION_L2_128B, CU_TENSOR_MAP_FLOAT_OOB_FILL_NONE);
  }
  {
    cuuint64_t dims[5] = {512, 2, 4, 4, 64}, st[4] = {1024, 8192, 2048, 32768};
    cuuint32_t box[5] = {64, 2, 4, 4, 4};
    enc(&mu, CU_TENSOR_MAP_DATA_TYPE_BFLOAT16, 5, d_in[4], dims, st, box, es, CU_TENSOR_MAP_INTERLEAVE_NONE,
        CU_TENSOR_MAP_SWIZZLE_128B, CU_TENSOR_MAP_L2_PROMOTION_L2_128B, CU_TENSOR_MAP_FLOAT_OOB_FILL_NONE);
  }
  {
    cuuint64_t dims[2] = {1024, 2048}, st[1] = {2048};
    cuuint32_t box[2] = {64, 16};
    enc(&mout, CU_TENSOR_MAP_DATA_TYPE_BFLOAT16, 2, d_out, dims, st, box, es, CU_TENSOR_MAP_INTERLEAVE_NONE,
        CU_TENSOR_MAP_SWIZZLE_128B, CU_TENSOR_MAP_L2_PROMOTION_NONE, CU_TENSOR_MAP_FLOAT_OOB_FILL_NONE);
  }
  Params P;
  P.x = (const __nv_bfloat16*)d_in[0];
  P.wphi = (const __nv_bfloat16*)d_in[2];
  P.wo = (const __nv_bfloat16*)d_in[3];
  P.u = (const __nv_bfloat16*)d_in[4];
  P.logA = (const __nv_bfloat16*)d_in[5];
  P.Aim = (const __nv_bfloat16*)d_in[6];
  P.Cre = (const __nv_bfloat16*)d_in[7];
  P.Cim = (const __nv_bfloat16*)d_in[8];
  P.logdt = (const __nv_bfloat16*)d_in[9];
  P.Dskip = (const __nv_bfloat16*)d_in[10];
  P.out = (__nv_bfloat16*)d_out;
  cudaFuncSetAttribute(fused_kernel, cudaFuncAttributeMaxDynamicSharedMemorySize, SMEM_BYTES);
  fused_kernel<<<NCTA, NTHREADS, SMEM_BYTES>>>(mx, mw, mo, mu, mout, P);
}
```

```cpp
#include <cuda_runtime.h>
#include <cuda_bf16.h>
#include <cuda_fp16.h>
#include <cuda.h>
#include <stdint.h>

#define DBG_TS 0

namespace {

constexpr int NTHREADS = 512;
constexpr int NCTA = 128;
constexpr int OFF_W = 0;
constexpr int OFF_X = 98304;
constexpr int OFF_U = OFF_X + 65536;
constexpr int U_CH = 4416, U_ODD = 2240, U_PAD = 128;
constexpr int OFF_STG0 = OFF_U + 18432;
constexpr int OFF_T = OFF_STG0 + 24576;
constexpr int T_CH = 5216;
constexpr int T_D = 0;
constexpr int T_5 = 2144;
constexpr int T_3 = T_5 + 384;
constexpr int T_7 = T_5 + 1024;
constexpr int T_9 = T_7 + 320;
constexpr int T_KC = T_9 + 320;
constexpr int T_ST = T_5 - 1024;
constexpr int OFF_PHI = OFF_T + 4 * T_CH;
constexpr int OFF_BAR = OFF_PHI + 1024;
constexpr int SMEM_BYTES = OFF_BAR + 512;
constexpr uint32_t SB = 1024;
static_assert(T_KC + 2 * 656 <= T_CH, "table size");
static_assert(SMEM_BYTES <= 232448, "smem");
constexpr int MB_FULL = 0  , MB_URAW = 16, MB_WO = 17  , MB_UFULL = 19, MB_ZOK = 20,
              MB_EMPTY = 21  , MB_RAWDONE = 37, MB_CLOSE = 38;
__host__ __device__ constexpr uint32_t BAR(int i) { return SB + OFF_BAR + 8 * i; }
constexpr int NB_WG0 = 1, NB_KPART = 2, NB_ST0 = 3  , NB_KV = 5, NB_RED = 6, NB_INIT = 7, NB_PREP = 8, NB_PROD = 9, NB_RDY = 10, NB_BDONE = 11, NB_ZERO = 12;
#define ZERO_N 1024
#define ZERO_STEP 7
#define STEPU -1
#define STEPPF 1
constexpr int STEP_PF = STEPPF, STEP_U = STEPU;
constexpr int SPIN_MAX = 1 << 16;

__device__ unsigned g_cnt[9 * 32];
__device__ uint4 g_uT[512 * 256];
__device__ uint4 g_part[16 * 8 * 144];
__device__ uint4 g_o[32 * 32 * 128];
__device__ uint4 g_y[512 * 8 * 32];
extern __shared__ uint8_t smem_raw[];
#define TS(i) do {} while (0)
#define TS1(i) do {} while (0)
#define GT(i) do {} while (0)

__device__ __forceinline__ uint32_t smem_u32(const void* p) { return (uint32_t)__cvta_generic_to_shared(p); }
__device__ __forceinline__ void mbar_arrive(uint32_t b) {
  asm volatile("mbarrier.arrive.shared::cta.b64 _, [%0];" ::"r"(b) : "memory");
}
__device__ __forceinline__ void mbar_wait(uint32_t b) {
  uint32_t done = 0;
#pragma unroll 1
  for (int i = 0; i < SPIN_MAX && !done; i++) {
    asm volatile("{\n.reg .pred p;\nmbarrier.try_wait.parity.shared::cta.b64 p, [%1], 0, 4000;\nselp.u32 %0, 1, 0, p;\n}\n"
                 : "=r"(done) : "r"(b) : "memory");
  }
}
__device__ __forceinline__ void mbar_init(uint32_t b, int n) {
  asm volatile("mbarrier.init.shared::cta.b64 [%0], %1;" ::"r"(b), "r"(n) : "memory");
}
__device__ __forceinline__ void mbar_expect(uint32_t b, int bytes) {
  asm volatile("mbarrier.arrive.expect_tx.shared::cta.b64 _, [%0], %1;" ::"r"(b), "r"(bytes) : "memory");
}
__device__ __forceinline__ void nb_sync(int id, int n) { asm volatile("bar.sync %0, %1;" ::"r"(id), "r"(n) : "memory"); }
__device__ __forceinline__ void nb_arrive(int id, int n) { asm volatile("bar.arrive %0, %1;" ::"r"(id), "r"(n) : "memory"); }
#define ELECT "{\n.reg .pred p;\nelect.sync _|p, 0xffffffff;\n@p "
__device__ __forceinline__ void e_expect(uint32_t b, int bytes) {
  asm volatile(ELECT "mbarrier.arrive.expect_tx.shared::cta.b64 _, [%0], %1;\n}\n" ::"r"(b), "r"(bytes) : "memory");
}
__device__ __forceinline__ void e_tma2d(uint32_t dst, const CUtensorMap* m, uint32_t bar, int c0, int c1) {
  asm volatile(ELECT "cp.async.bulk.tensor.2d.shared::cluster.global.mbarrier::complete_tx::bytes [%0], [%1, {%3,%4}], [%2];\n}\n"
               ::"r"(dst), "l"(m), "r"(bar), "r"(c0), "r"(c1) : "memory");
}
__device__ __forceinline__ void e_tma3d(uint32_t dst, const CUtensorMap* m, uint32_t bar, int c0, int c1, int c2) {
  asm volatile(ELECT "cp.async.bulk.tensor.3d.shared::cluster.global.mbarrier::complete_tx::bytes [%0], [%1, {%3,%4,%5}], [%2];\n}\n"
               ::"r"(dst), "l"(m), "r"(bar), "r"(c0), "r"(c1), "r"(c2) : "memory");
}
__device__ __forceinline__ void e_tma5d(uint32_t dst, const CUtensorMap* m, uint32_t bar, int c0, int c4) {
  asm volatile(ELECT "cp.async.bulk.tensor.5d.shared::cluster.global.mbarrier::complete_tx::bytes [%0], [%1, {%3,%5,%5,%5,%4}], [%2];\n}\n"
               ::"r"(dst), "l"(m), "r"(bar), "r"(c0), "r"(c4), "r"(0) : "memory");
}
__device__ __forceinline__ void e_bulk(uint32_t dst, const void* src, int bytes, uint32_t bar) {
  asm volatile(ELECT "cp.async.bulk.shared::cluster.global.mbarrier::complete_tx::bytes [%0], [%1], %2, [%3];\n}\n"
               ::"r"(dst), "l"(src), "r"(bytes), "r"(bar) : "memory");
}
__device__ __forceinline__ void e_prefetch(const void* p, int bytes) {
  asm volatile(ELECT "cp.async.bulk.prefetch.L2.global [%0], %1;\n}\n" ::"l"(p), "r"(bytes) : "memory");
}
__device__ __forceinline__ void e_store2d(const CUtensorMap* m, uint32_t src, int c0, int c1) {
  asm volatile(ELECT "cp.async.bulk.tensor.2d.global.shared::cta.bulk_group [%0, {%2,%3}], [%1];\n"
               "@p cp.async.bulk.commit_group;\n@p cp.async.bulk.wait_group.read 0;\n}\n"
               ::"l"(m), "r"(src), "r"(c0), "r"(c1) : "memory");
}
__host__ __device__ constexpr uint64_t mkdesc(uint32_t addr, uint32_t lbo, uint32_t sbo, int swz) {
  return (uint64_t)((addr & 0x3FFFF) >> 4) | ((uint64_t)(lbo >> 4) << 16) | ((uint64_t)(sbo >> 4) << 32) |
         ((uint64_t)swz << 62);
}
#define WG_FENCE() asm volatile("wgmma.fence.sync.aligned;" ::: "memory")
#define WG_COMMIT() asm volatile("wgmma.commit_group.sync.aligned;" ::: "memory")
#define WG_WAIT(n) asm volatile("wgmma.wait_group.sync.aligned " #n ";" ::: "memory")

__device__ __forceinline__ void mma(float& d0, float& d1, float& d2, float& d3, uint32_t a0, uint32_t a1, uint32_t a2,
                                    uint32_t a3, uint32_t b0, uint32_t b1) {
  asm volatile("mma.sync.aligned.m16n8k16.row.col.f32.bf16.bf16.f32 {%0,%1,%2,%3},{%4,%5,%6,%7},{%8,%9},{%0,%1,%2,%3};"
               : "+f"(d0), "+f"(d1), "+f"(d2), "+f"(d3)
               : "r"(a0), "r"(a1), "r"(a2), "r"(a3), "r"(b0), "r"(b1));
}
__device__ __forceinline__ void mmac(float (&d)[4], uint32_t a0, uint32_t a1, uint32_t a2, uint32_t a3, uint32_t b0,
                                     uint32_t b1, const float (&c)[4]) {
  asm volatile("mma.sync.aligned.m16n8k16.row.col.f32.bf16.bf16.f32 {%0,%1,%2,%3},{%4,%5,%6,%7},{%8,%9},{%10,%11,%12,%13};"
               : "=f"(d[0]), "=f"(d[1]), "=f"(d[2]), "=f"(d[3])
               : "r"(a0), "r"(a1), "r"(a2), "r"(a3), "r"(b0), "r"(b1), "f"(c[0]), "f"(c[1]), "f"(c[2]), "f"(c[3]));
}
__device__ __forceinline__ void mma_p(int p, float (&d)[4], uint32_t a0, uint32_t a1, uint32_t a2, uint32_t a3, uint32_t b0, uint32_t b1) {
  asm volatile("{\n.reg .pred q;\nsetp.ne.b32 q, %10, 0;\n"
               "@q mma.sync.aligned.m16n8k16.row.col.f32.bf16.bf16.f32 {%0,%1,%2,%3},{%4,%5,%6,%7},{%8,%9},{%0,%1,%2,%3};\n}\n"
               : "+f"(d[0]), "+f"(d[1]), "+f"(d[2]), "+f"(d[3])
               : "r"(a0), "r"(a1), "r"(a2), "r"(a3), "r"(b0), "r"(b1), "r"(p));
}
__device__ __forceinline__ void mmac_p(int p, float (&d)[4], uint32_t a0, uint32_t a1, uint32_t a2, uint32_t a3, uint32_t b0,
                                       uint32_t b1, const float (&c)[4]) {
  asm volatile("{\n.reg .pred q;\nsetp.ne.b32 q, %14, 0;\n"
               "@q mma.sync.aligned.m16n8k16.row.col.f32.bf16.bf16.f32 {%0,%1,%2,%3},{%4,%5,%6,%7},{%8,%9},{%10,%11,%12,%13};\n}\n"
               : "+f"(d[0]), "+f"(d[1]), "+f"(d[2]), "+f"(d[3])
               : "r"(a0), "r"(a1), "r"(a2), "r"(a3), "r"(b0), "r"(b1), "f"(c[0]), "f"(c[1]), "f"(c[2]), "f"(c[3]), "r"(p));
}
__device__ __forceinline__ void mma_k8(float (&d)[4], uint32_t a0, uint32_t a1, uint32_t b0) {
  asm volatile("mma.sync.aligned.m16n8k8.row.col.f32.bf16.bf16.f32 {%0,%1,%2,%3},{%4,%5},{%6},{%0,%1,%2,%3};"
               : "+f"(d[0]), "+f"(d[1]), "+f"(d[2]), "+f"(d[3]) : "r"(a0), "r"(a1), "r"(b0));
}
__device__ __forceinline__ void mma0(float& d0, float& d1, float& d2, float& d3, uint32_t a0, uint32_t a1, uint32_t a2,
                                     uint32_t a3, uint32_t b0, uint32_t b1) {
  asm volatile("mma.sync.aligned.m16n8k16.row.col.f32.bf16.bf16.f32 {%0,%1,%2,%3},{%4,%5,%6,%7},{%8,%9},{%10,%10,%10,%10};"
               : "=f"(d0), "=f"(d1), "=f"(d2), "=f"(d3)
               : "r"(a0), "r"(a1), "r"(a2), "r"(a3), "r"(b0), "r"(b1), "f"(0.f));
}
__device__ __forceinline__ uint32_t pack_bf(float lo, float hi) {
  uint32_t r;
  asm("cvt.rn.bf16x2.f32 %0, %1, %2;" : "=r"(r) : "f"(hi), "f"(lo));
  return r;
}
__device__ __forceinline__ float bf_lo(uint32_t w) { return __uint_as_float(w << 16); }
__device__ __forceinline__ float bf_hi(uint32_t w) { return __uint_as_float(w & 0xffff0000u); }
__device__ __forceinline__ float bf_round(float x) { return __bfloat162float(__float2bfloat16_rn(x)); }
__device__ __forceinline__ uint32_t bmax2(uint32_t a, uint32_t b) {
  uint32_t r; asm("max.bf16x2 %0, %1, %2;" : "=r"(r) : "r"(a), "r"(b)); return r;
}
__device__ __forceinline__ uint32_t bmin2(uint32_t a, uint32_t b) {
  uint32_t r; asm("min.bf16x2 %0, %1, %2;" : "=r"(r) : "r"(a), "r"(b)); return r;
}
__device__ __forceinline__ float ex2(float x) { float r; asm("ex2.approx.ftz.f32 %0, %1;" : "=f"(r) : "f"(x)); return r; }
__device__ __forceinline__ float rcp(float x) { float r; asm("rcp.approx.ftz.f32 %0, %1;" : "=f"(r) : "f"(x)); return r; }
__device__ __forceinline__ void ldsm4(uint32_t (&r)[4], uint32_t a) {
  asm volatile("ldmatrix.sync.aligned.m8n8.x4.shared.b16 {%0,%1,%2,%3}, [%4];"
               : "=r"(r[0]), "=r"(r[1]), "=r"(r[2]), "=r"(r[3]) : "r"(a) : "memory");
}
__device__ __forceinline__ void ldsm4t(uint32_t (&r)[4], uint32_t a) {
  asm volatile("ldmatrix.sync.aligned.m8n8.x4.trans.shared.b16 {%0,%1,%2,%3}, [%4];"
               : "=r"(r[0]), "=r"(r[1]), "=r"(r[2]), "=r"(r[3]) : "r"(a) : "memory");
}
__device__ __forceinline__ void stsm4(uint32_t a, uint32_t r0, uint32_t r1, uint32_t r2, uint32_t r3) {
  asm volatile("stmatrix.sync.aligned.m8n8.x4.shared.b16 [%0], {%1,%2,%3,%4};"
               ::"r"(a), "r"(r0), "r"(r1), "r"(r2), "r"(r3) : "memory");
}
__device__ __forceinline__ uint32_t lds32(uint32_t a) {
  uint32_t r; asm volatile("ld.shared.u32 %0, [%1];" : "=r"(r) : "r"(a) : "memory"); return r;
}
__device__ __forceinline__ uint32_t lds16(uint32_t a) {
  uint32_t r; asm volatile("{\n.reg .u16 h;\nld.shared.u16 h, [%1];\ncvt.u32.u16 %0, h;\n}\n" : "=r"(r) : "r"(a) : "memory"); return r;
}
__device__ __forceinline__ uint2 lds64(uint32_t a) {
  uint2 r; asm volatile("ld.shared.v2.u32 {%0,%1}, [%2];" : "=r"(r.x), "=r"(r.y) : "r"(a) : "memory"); return r;
}
__device__ __forceinline__ uint4 lds128(uint32_t a) {
  uint4 r;
  asm volatile("ld.shared.v4.u32 {%0,%1,%2,%3}, [%4];" : "=r"(r.x), "=r"(r.y), "=r"(r.z), "=r"(r.w) : "r"(a) : "memory");
  return r;
}
__device__ __forceinline__ void sts32(uint32_t a, uint32_t v) { asm volatile("st.shared.u32 [%0], %1;" ::"r"(a), "r"(v) : "memory"); }
__device__ __forceinline__ void sts16(uint32_t a, uint32_t v) {
  asm volatile("{\n.reg .u16 h;\ncvt.u16.u32 h, %1;\nst.shared.u16 [%0], h;\n}\n" ::"r"(a), "r"(v) : "memory");
}
__device__ __forceinline__ void sts64(uint32_t a, uint32_t x, uint32_t y) {
  asm volatile("st.shared.v2.u32 [%0], {%1,%2};" ::"r"(a), "r"(x), "r"(y) : "memory");
}
__device__ __forceinline__ void sts128(uint32_t a, uint32_t x, uint32_t y, uint32_t z, uint32_t w) {
  asm volatile("st.shared.v4.u32 [%0], {%1,%2,%3,%4};" ::"r"(a), "r"(x), "r"(y), "r"(z), "r"(w) : "memory");
}
__device__ __forceinline__ uint4 ld_x(const uint4* p) {
  uint4 r;
  asm volatile("{\n.reg .b128 t;\nld.relaxed.gpu.global.b128 t, [%4];\nmov.b128 {%0,%1,%2,%3}, t;\n}\n"
               : "=r"(r.x), "=r"(r.y), "=r"(r.z), "=r"(r.w) : "l"(p) : "memory");
  return r;
}
__device__ __forceinline__ uint32_t ld_x32(const uint32_t* p) {
  uint32_t r; asm volatile("ld.relaxed.gpu.global.u32 %0, [%1];" : "=r"(r) : "l"(p) : "memory"); return r;
}
__device__ __forceinline__ void st_x(uint4* p, uint32_t x, uint32_t y, uint32_t z, uint32_t w) {
  asm volatile("{\n.reg .b128 t;\nmov.b128 t, {%1,%2,%3,%4};\nst.relaxed.gpu.global.b128 [%0], t;\n}\n"
               ::"l"(p), "r"(x), "r"(y), "r"(z), "r"(w) : "memory");
}
__device__ __forceinline__ void st_x_p(int p, uint4* a, uint32_t x, uint32_t y, uint32_t z, uint32_t w) {
  asm volatile("{\n.reg .b128 t;\n.reg .pred q;\nsetp.ne.b32 q, %5, 0;\nmov.b128 t, {%1,%2,%3,%4};\n@q st.relaxed.gpu.global.b128 [%0], t;\n}\n"
               ::"l"(a), "r"(x), "r"(y), "r"(z), "r"(w), "r"(p) : "memory");
}
__device__ __forceinline__ void sts64_p(int p, uint32_t a, uint32_t x, uint32_t y) {
  asm volatile("{\n.reg .pred q;\nsetp.ne.b32 q, %3, 0;\n@q st.shared.v2.u32 [%0], {%1,%2};\n}\n" ::"r"(a), "r"(x), "r"(y), "r"(p) : "memory");
}
__device__ __forceinline__ void st_x32(uint32_t* p, uint32_t x) {
  asm volatile("st.relaxed.gpu.global.u32 [%0], %1;" ::"l"(p), "r"(x) : "memory");
}
__device__ __forceinline__ uint32_t nz(uint32_t w) { return max(w, 1u); }
__device__ __forceinline__ uint32_t fu(float x) { return __float_as_uint(x); }
__device__ __forceinline__ float uf(uint32_t x) { return __uint_as_float(x); }

__device__ __forceinline__ void wgmma_ss_n96(float (&d)[48], uint64_t da, uint64_t db, int sc) {
  asm volatile("{\n.reg .pred p;\nsetp.ne.b32 p, %50, 0;\n"
      "wgmma.mma_async.sync.aligned.m64n96k16.f32.bf16.bf16 "
      "{%0,%1,%2,%3,%4,%5,%6,%7,%8,%9,%10,%11,%12,%13,%14,%15,%16,%17,%18,%19,%20,%21,%22,%23,%24,%25,%26,%27,%28,%29,%30,%31,%32,%33,%34,%35,%36,%37,%38,%39,%40,%41,%42,%43,%44,%45,%46,%47}, "
      "%48, %49, p, 1, 1, 0, 1;\n}\n"
      : "+f"(d[0]), "+f"(d[1]), "+f"(d[2]), "+f"(d[3]), "+f"(d[4]), "+f"(d[5]), "+f"(d[6]), "+f"(d[7]),
        "+f"(d[8]), "+f"(d[9]), "+f"(d[10]), "+f"(d[11]), "+f"(d[12]), "+f"(d[13]), "+f"(d[14]), "+f"(d[15]),
        "+f"(d[16]), "+f"(d[17]), "+f"(d[18]), "+f"(d[19]), "+f"(d[20]), "+f"(d[21]), "+f"(d[22]), "+f"(d[23]),
        "+f"(d[24]), "+f"(d[25]), "+f"(d[26]), "+f"(d[27]), "+f"(d[28]), "+f"(d[29]), "+f"(d[30]), "+f"(d[31]),
        "+f"(d[32]), "+f"(d[33]), "+f"(d[34]), "+f"(d[35]), "+f"(d[36]), "+f"(d[37]), "+f"(d[38]), "+f"(d[39]),
        "+f"(d[40]), "+f"(d[41]), "+f"(d[42]), "+f"(d[43]), "+f"(d[44]), "+f"(d[45]), "+f"(d[46]), "+f"(d[47])
      : "l"(da), "l"(db), "r"(sc));
}

__device__ __forceinline__ void wgmma_rs_n128(float (&d)[64], const uint4& a, uint64_t db, int sc) {
  asm volatile("{\n.reg .pred p;\nsetp.ne.b32 p, %69, 0;\n"
      "wgmma.mma_async.sync.aligned.m64n128k16.f32.bf16.bf16 "
      "{%0,%1,%2,%3,%4,%5,%6,%7,%8,%9,%10,%11,%12,%13,%14,%15,%16,%17,%18,%19,%20,%21,%22,%23,%24,%25,%26,%27,%28,%29,%30,%31,%32,%33,%34,%35,%36,%37,%38,%39,%40,%41,%42,%43,%44,%45,%46,%47,%48,%49,%50,%51,%52,%53,%54,%55,%56,%57,%58,%59,%60,%61,%62,%63}, "
      "{%64,%65,%66,%67}, %68, p, 1, 1, 1;\n}\n"
      : "+f"(d[0]), "+f"(d[1]), "+f"(d[2]), "+f"(d[3]), "+f"(d[4]), "+f"(d[5]), "+f"(d[6]), "+f"(d[7]),
        "+f"(d[8]), "+f"(d[9]), "+f"(d[10]), "+f"(d[11]), "+f"(d[12]), "+f"(d[13]), "+f"(d[14]), "+f"(d[15]),
        "+f"(d[16]), "+f"(d[17]), "+f"(d[18]), "+f"(d[19]), "+f"(d[20]), "+f"(d[21]), "+f"(d[22]), "+f"(d[23]),
        "+f"(d[24]), "+f"(d[25]), "+f"(d[26]), "+f"(d[27]), "+f"(d[28]), "+f"(d[29]), "+f"(d[30]), "+f"(d[31]),
        "+f"(d[32]), "+f"(d[33]), "+f"(d[34]), "+f"(d[35]), "+f"(d[36]), "+f"(d[37]), "+f"(d[38]), "+f"(d[39]),
        "+f"(d[40]), "+f"(d[41]), "+f"(d[42]), "+f"(d[43]), "+f"(d[44]), "+f"(d[45]), "+f"(d[46]), "+f"(d[47]),
        "+f"(d[48]), "+f"(d[49]), "+f"(d[50]), "+f"(d[51]), "+f"(d[52]), "+f"(d[53]), "+f"(d[54]), "+f"(d[55]),
        "+f"(d[56]), "+f"(d[57]), "+f"(d[58]), "+f"(d[59]), "+f"(d[60]), "+f"(d[61]), "+f"(d[62]), "+f"(d[63])
      : "r"(a.x), "r"(a.y), "r"(a.z), "r"(a.w), "l"(db), "r"(sc));
}

struct Params {
  const __nv_bfloat16 *x, *wphi, *wo, *u, *logA, *Aim, *Cre, *Cim, *logdt, *Dskip;
  __nv_bfloat16* out;
};

__device__ __forceinline__ uint4 tr_row(const uint4 (&v)[8], int i) {
  uint32_t o[4];
#pragma unroll
  for (int m = 0; m < 4; m++) {
    const uint4 &ra = v[2 * m], &rb = v[2 * m + 1];
    const int k = i >> 1;
    const uint32_t xa = k == 0 ? ra.x : k == 1 ? ra.y : k == 2 ? ra.z : ra.w;
    const uint32_t xb = k == 0 ? rb.x : k == 1 ? rb.y : k == 2 ? rb.z : rb.w;
    o[m] = __byte_perm(xa, xb, (i & 1) ? 0x7632 : 0x5410);
  }
  return make_uint4(o[0], o[1], o[2], o[3]);
}

struct cpx { float r, i; };
__device__ __forceinline__ cpx cmul(cpx a, cpx b) { return {a.r * b.r - a.i * b.i, a.r * b.i + a.i * b.r}; }
__device__ __forceinline__ cpx csq(cpx a) { return {a.r * a.r - a.i * a.i, 2.f * (a.r * a.i)}; }
__device__ __forceinline__ cpx polar(float e, float t) {
  const float m = ex2(e);
  return {m * __cosf(t), m * __sinf(t)};
}

__device__ __forceinline__ void kgen_round(const Params& P, int d, int m0, int cnt, int lane, float& dt, uint32_t open_bar,
                                           float (&k)[5][4], float& k2048) {
  const int g = lane >> 2, c = lane & 3;
  uint32_t Q[6][14];
  {
    const int o = d * 128 + m0 + 2 * cnt * c;
    const __nv_bfloat16* src[4] = {P.logA, P.Aim, P.Cre, P.Cim};
#pragma unroll
    for (int j = 0; j < 3; j++)
#pragma unroll
      for (int a = 0; a < 4; a++) {
        uint2 v = make_uint2(0, 0);
        if (j < 2 || cnt > 4) v = __ldg((const uint2*)(src[a] + o) + j);
        Q[2 * j + 1][4 + 2 * a] = v.x; Q[2 * j + 1][5 + 2 * a] = v.y;
      }
  }
  dt = bf_round(expf(__bfloat162float(P.logdt[d])));
  const float pg = (float)g;
  const float n2 = (float)(4 + 2 * (g & 1)), m2 = (float)(g & 6), p2 = 64.f * n2 + m2;
  const float n3 = (float)(8 + 2 * (g & 3)), m3 = (float)(g & 4), p3 = 64.f * n3 + m3;
  const float n4 = (float)(16 + 2 * g), p4 = 64.f * n4;
  const float ca = dt * -1.4426950408889634f, c64 = dt * 10.185916357881302f;
  uint32_t la = Q[1][4], ai = Q[1][6], cr = Q[1][8], ci = Q[1][10];
#pragma unroll 1
  for (int s = 0; s < cnt; s++) {
    uint32_t o[14];
    const uint32_t ar = pack_bf(ex2(bf_lo(la) * 1.4426950408889634f), ex2(bf_hi(la) * 1.4426950408889634f));
#pragma unroll
    for (int h = 0; h < 2; h++) {
      const float a2 = (h ? bf_hi(ar) : bf_lo(ar)) * ca, im = h ? bf_hi(ai) : bf_lo(ai);
      const float f = im * dt;
      const float f64 = fmaf(im, c64, 12582912.f - fmaf(im, c64, 12582912.f)) * 6.283185307179586f;
      const cpx C = {h ? bf_hi(cr) : bf_lo(cr), h ? bf_hi(ci) : bf_lo(ci)};
      const cpx w64 = polar(a2 * 64.f, f64);
      const cpx d1 = polar(a2 * pg, f * pg);
      const cpx t2 = polar(a2 * p2, fmaf(f64, n2, f * m2));
      const cpx t3 = polar(a2 * p3, fmaf(f64, n3, f * m3));
      const cpx t4 = polar(a2 * p4, f64 * n4);
      const cpx s8 = csq(csq(csq(d1)));
      const cpx a0 = cmul(C, s8), a1 = cmul(a0, w64);
      const cpx t1 = cmul(d1, csq(w64));
      const cpx ce = cmul(C, t4);
      k2048 += ce.r * t4.r - ce.i * t4.i;
      o[2 * h] = pack_bf(a0.r, -a0.i);
      o[2 * h + 1] = pack_bf(a1.r, -a1.i);
      o[4 + h] = pack_bf(d1.r, d1.i);
      o[6 + h] = pack_bf(t1.r, t1.i);
      o[8 + h] = pack_bf(t2.r, t2.i);
      o[10 + h] = pack_bf(t3.r, t3.i);
      o[12 + h] = pack_bf(t4.r, t4.i);
    }
#define MV(d_, s_) asm volatile("mov.b32 %0, %1;" : "=r"(d_) : "r"(s_))
#define KQ(i) case i: \
      if (i < 5) { MV(la, Q[(i + 1) % 6 | 1][4 + ((i + 1) & 1)]); MV(ai, Q[(i + 1) % 6 | 1][6 + ((i + 1) & 1)]); \
                   MV(cr, Q[(i + 1) % 6 | 1][8 + ((i + 1) & 1)]); MV(ci, Q[(i + 1) % 6 | 1][10 + ((i + 1) & 1)]); } \
      _Pragma("unroll") for (int e = 0; e < 14; e++) MV(Q[i][e], o[e]); break;
    switch (s) { KQ(0) KQ(1) KQ(2) KQ(3) KQ(4) default: KQ(5) }
#undef KQ
#undef MV
  }
  TS(40 + (m0 >> 5));
  if (cnt > 4) nb_sync(NB_PREP, 288);
  mbar_wait(open_bar);
#pragma unroll
  for (int s = 0; s < 4; s++)
#pragma unroll
    for (int j = 0; j < 5; j++) mma(k[j][0], k[j][1], k[j][2], k[j][3], Q[s][0], Q[s][1], Q[s][2], Q[s][3], Q[s][4 + 2 * j], Q[s][5 + 2 * j]);
  if (cnt > 4) {
#pragma unroll
    for (int s = 4; s < 6; s++)
#pragma unroll
      for (int j = 0; j < 5; j++) mma(k[j][0], k[j][1], k[j][2], k[j][3], Q[s][0], Q[s][1], Q[s][2], Q[s][3], Q[s][4 + 2 * j], Q[s][5 + 2 * j]);
  }
}

__device__ __forceinline__ void build_tables(uint32_t tb, int lane, float (&k)[5][4], float k2048) {
  const int g = lane >> 2, c = lane & 3;
  const uint32_t kc = tb + T_KC + 16;
  {
    const uint32_t a0 = kc + 16 * g + 4 * c, a2 = kc + 2 * (256 + 4 * g + c);
    const uint32_t a3 = kc + 2 * (384 + 2 * g + 64 * (c & 1) + (c >> 1)), a4 = kc + 2 * (512 + g + 32 * c);
#pragma unroll
    for (int r = 0; r < 2; r++) {
      sts32(a0 + 128 * r, pack_bf(k[0][2 * r], k[0][2 * r + 1]));
      sts32(a0 + 128 * r + 256, pack_bf(k[1][2 * r], k[1][2 * r + 1]));
      const uint32_t w2 = pack_bf(k[2][2 * r], k[2][2 * r + 1]);
      const uint32_t w3 = pack_bf(k[3][2 * r], k[3][2 * r + 1]);
      const uint32_t w4 = pack_bf(k[4][2 * r], k[4][2 * r + 1]);
      sts16(a2 + 64 * r, w2); sts16(a2 + 64 * r + 128, w2 >> 16);
      sts16(a3 + 32 * r, w3); sts16(a3 + 32 * r + 64, w3 >> 16);
      sts16(a4 + 16 * r, w4); sts16(a4 + 16 * r + 32, w4 >> 16);
    }
  }
  if (lane == 0) { sts16(kc + 2 * 640, pack_bf(k2048, 0.f)); sts16(kc - 2, 0); }
  __syncwarp();
  const uint32_t td = tb + T_D + 32;
  {
    const uint4 v = lds128(kc + 16 * lane);
    const uint32_t pv = lds16(kc + 16 * lane - 2);
    sts128(td + 32 * lane, __byte_perm(v.x, pv, 0x5410), __byte_perm(v.x, v.x, 0x1032), __byte_perm(v.y, v.x, 0x7610),
           __byte_perm(v.y, v.y, 0x1032));
    sts128(td + 32 * lane + 16, __byte_perm(v.z, v.y, 0x7610), __byte_perm(v.z, v.z, 0x1032),
           __byte_perm(v.w, v.z, 0x7610), __byte_perm(v.w, v.w, 0x1032));
  }
  {
    const uint2 v = lds64(kc + 512 + 8 * lane);
    const uint32_t k4 = lds16(kc + 512 + 8 * lane + 8);
    const uint32_t pv = lds16(kc + (lane == 0 ? 510 : 512 + 8 * lane));
    const uint32_t k22 = __byte_perm(v.y, v.y, 0x1010);
    sts128(td + 1024 + 32 * lane, __byte_perm(v.x, pv, 0x5410), __byte_perm(v.x, v.x, 0x1010),
           __byte_perm(v.x, v.x, 0x1032), __byte_perm(v.y, v.x, 0x7610));
    sts128(td + 1024 + 32 * lane + 16, k22, k22, __byte_perm(v.y, v.y, 0x1032), __byte_perm(k4, v.y, 0x7610));
  }
  {
    const uint32_t kk = lds16(kc + 2 * 384);
    const uint32_t w = lane < 3 ? (kk | (kk << 16)) : (lane == 3 ? (kk << 16) : 0u);
    if (lane < 24) sts32(td + 4 * (lane < 16 ? 512 + lane : lane - 24), w);
    const uint32_t lo_ = lds16(kc + 2 * 511), le_ = lds16(kc + 2 * 512);
    const uint32_t ja = tb + T_5 + (lane < 16 ? 4 * lane : 256 + 4 * lane);
    sts32(ja, lane == 16 ? (le_ << 16) : 0u);
    sts32(ja + 384, lane == 16 ? (lo_ << 16) : 0u);
    sts32(tb + (lane < 16 ? T_7 : T_9 - 64) + 4 * lane, 0u);
  }
#pragma unroll
  for (int s = 0; s < 2; s++) {
    const uint32_t b = kc + 2 * (s ? 512 : 384) + 8 * lane;
    const uint2 v = lds64(b);
    uint32_t em = lds16(b - 2), e0 = v.x;
    const uint32_t e4 = lds16(b + 8);
    if (lane == 0) { em = 0; e0 = 0; }
    sts64(tb + (s ? T_7 : T_3) + 64 + 8 * lane, __byte_perm(v.x, em, 0x5432), __byte_perm(v.y, v.x, 0x7632));
    sts64(tb + (s ? T_9 : T_5) + 64 + 8 * lane, __byte_perm(v.y, e0, 0x5410), __byte_perm(e4, v.y, 0x5410));
  }
  __syncwarp();
}

__device__ __forceinline__ uint32_t box2w(int lo, int n, int o) {
  return ((unsigned)(o - lo) < (unsigned)n ? 0x3F80u : 0u) | ((unsigned)(o + 1 - lo) < (unsigned)n ? 0x3F800000u : 0u);
}

__device__ __forceinline__ void conv_channel(uint32_t ub, uint32_t tb, int lane, uint4* ydst) {
  const int g = lane >> 2, c = lane & 3, x = g - 2 * c;
  const uint32_t st = tb + T_ST + lane * 8;
  const int mi = lane >> 3;
  const uint32_t qa = ub + U_PAD + 16 * (lane & 7) + ((mi == 0 || mi == 3) ? U_ODD : 0) - (mi == 0 ? 16 : 0);
  const uint32_t kv = lds16(tb + T_KC + 16 + 2 * 512);
  {
    const uint32_t hb = ub + U_PAD + (mi & 1) * U_ODD + 16 * ((lane >> 4) + (lane & 7)) - 16;
    const int oh = c < 2 ? 8 + 2 * c : 2 * c - 8;
    const uint32_t bx0 = box2w(g - 4, 9, 2 * c), bx1 = box2w(g - 3, 7, 2 * c), bx2 = box2w(g - 4, 9, oh), bx3 = box2w(g - 3, 7, oh);
    uint32_t f7[9], f9a[9], f9b[9];
    const uint32_t fa = tb + T_7 + 4 * (8 + x);
#pragma unroll
    for (int m = 0; m < 9; m++) {
      f7[m] = lds32(fa + 32 * m);
      f9b[m] = lds32(fa + 320 + 32 * m);
      f9a[m] = lds32(fa + 316 + 32 * m);
    }
    TS(36);
    uint32_t z09[8], z07[8], zm9[8], zm7[8];
#pragma unroll
    for (int i = 0; i < 8; i++) {
      uint32_t h[4];
      ldsm4(h, hb + 128 * i);
      float y0, y1, y2, y3, w0, w1, w2, w3;
      mma0(y0, y1, y2, y3, bx0, bx1, bx2, bx3, h[2], c < 2 ? h[3] : h[1]);
      mma0(w0, w1, w2, w3, bx0, bx1, bx2, bx3, h[1], c < 2 ? h[2] : h[0]);
      z09[i] = pack_bf(y0, y1); z07[i] = pack_bf(y2, y3);
      zm9[i] = pack_bf(w0, w1); zm7[i] = pack_bf(w2, w3);
    }
    float a[4][2][4];
#pragma unroll
    for (int kap = 0; kap < 4; kap++)
#pragma unroll
      for (int sg = 0; sg < 2; sg++)
#pragma unroll
        for (int bk = 3; bk >= kap; bk--) {
          const int m = 2 * (bk - kap) + 1;
          float(&a0)[4] = a[bk][0];
          float(&a1)[4] = a[bk][1];
          if (sg == 0 && kap == 0) {
            mma0(a0[0], a0[1], a0[2], a0[3], f9a[m], f9a[m + 1], f9a[m - 1], f9a[m], z09[0], z09[1]);
            mma0(a1[0], a1[1], a1[2], a1[3], f9b[m], f9b[m + 1], f9b[m - 1], f9b[m], zm9[0], zm9[1]);
          } else if (sg == 0) {
            mma(a0[0], a0[1], a0[2], a0[3], f9a[m], f9a[m + 1], f9a[m - 1], f9a[m], z09[2 * kap], z09[2 * kap + 1]);
            mma(a1[0], a1[1], a1[2], a1[3], f9b[m], f9b[m + 1], f9b[m - 1], f9b[m], zm9[2 * kap], zm9[2 * kap + 1]);
          } else {
            mma(a0[0], a0[1], a0[2], a0[3], f7[m], f7[m + 1], f7[m - 1], f7[m], zm7[2 * kap], zm7[2 * kap + 1]);
            mma(a1[0], a1[1], a1[2], a1[3], f7[m], f7[m + 1], f7[m - 1], f7[m], z07[2 * kap], z07[2 * kap + 1]);
          }
        }
#pragma unroll
    for (int bk = 0; bk < 4; bk++) {
      sts64(st + 256 * (8 + 2 * bk), pack_bf(a[bk][0][0], a[bk][0][1]), pack_bf(a[bk][1][0], a[bk][1][1]));
      sts64(st + 256 * (9 + 2 * bk), pack_bf(a[bk][0][2], a[bk][0][3]), pack_bf(a[bk][1][2], a[bk][1][3]));
    }
  }
  TS(44);
  {
    const int oh = c < 3 ? 2 * c : -10;
    const uint32_t bx0 = box2w(g - 10, 5, 2 * c - 8), bx1 = box2w(g - 5, 3, 2 * c - 8), bx2 = box2w(g - 10, 5, oh), bx3 = box2w(g - 5, 3, oh);
    const uint32_t lb0 = ((unsigned)(x + 5) < 2u ? kv : 0u) | ((unsigned)(x + 4) < 2u ? kv << 16 : 0u);
    const uint32_t lb1 = ((unsigned)(x - 3) < 2u ? kv : 0u) | ((unsigned)(x - 4) < 2u ? kv << 16 : 0u);
    const int q0 = g - 1, q1 = c < 3 ? g : g - 2;
    uint32_t y0a = ub + U_PAD + (q0 & 1) * U_ODD + 16 * (q0 >> 1) + 4 * c;
    uint32_t y1a = ub + U_PAD + (q1 & 1) * U_ODD + 16 * (q1 >> 1) + 4 * c;
    uint2 a5[10], a3[10];
    const uint32_t aa = tb + T_5 + 4 * (8 + 2 * g - 2 * c);
#pragma unroll
    for (int m = 0; m < 10; m++) { a5[m] = lds64(aa + 32 * m); a3[m] = lds64(aa + 384 + 32 * m); }
    float T[6][4];
#pragma unroll
    for (int i = 0; i < 6; i++) T[i][0] = T[i][1] = T[i][2] = T[i][3] = 0.f;
    uint32_t x5[2] = {0, 0}, x3[2] = {0, 0}, yb[4], lq[4];
    uint32_t lqa = qa, sta = st + 256 * 8;
    uint2 sv;
    auto fetch = [&]() {
      yb[0] = lds32(y0a); yb[1] = lds32(y1a); yb[2] = lds32(y0a + 64); yb[3] = lds32(y1a + 64);
      ldsm4(lq, lqa);
      sv = lds64(min(sta, st + 256 * 15));
      y0a += 128; y1a += 128; lqa += 128; sta += 256;
    };
    fetch();
#pragma unroll 2
    for (int kap = -1; kap < 13; kap++) {
      float yn[2][4];
      mma0(yn[0][0], yn[0][1], yn[0][2], yn[0][3], bx0, bx1, bx2, bx3, yb[0], yb[1]);
      mma0(yn[1][0], yn[1][1], yn[1][2], yn[1][3], bx0, bx1, bx2, bx3, yb[2], yb[3]);
      sts64_p(kap > 0, sta - 256 * 7, pack_bf(T[0][0], T[0][1]), pack_bf(T[0][2], T[0][3]));
#pragma unroll
      for (int i = 0; i < 5; i++)
        mmac_p((unsigned)kap < 12u - i, T[i], a5[2 * i + 1].x, a5[2 * i + 1].y, a5[2 * i].x, a5[2 * i].y, x5[0], x5[1], T[i + 1]);
      const float ci[4] = {bf_lo(sv.x), bf_hi(sv.x), bf_lo(sv.y), bf_hi(sv.y)};
      mmac_p(kap < 7, T[5], lq[0], lq[1], lq[2], lq[3], lb0, lb1, ci);
      fetch();
#pragma unroll
      for (int i = 0; i < 5; i++)
        mma_p((unsigned)kap < 12u - i, T[i], a3[2 * i + 1].x, a3[2 * i + 1].y, a3[2 * i].x, a3[2 * i].y, x3[0], x3[1]);
#pragma unroll
      for (int hh = 0; hh < 2; hh++) { x5[hh] = pack_bf(yn[hh][0], yn[hh][1]); x3[hh] = pack_bf(yn[hh][2], yn[hh][3]); }
    }
  }
  TS(45);
  {
    uint32_t F[66];
    const uint32_t fa = tb + T_D + 32 + 4 * x;
#pragma unroll
    for (int m = 0; m < 66; m++) F[m] = lds32(fa + 32 * m);
    float T[5][4];
#pragma unroll
    for (int i = 0; i < 5; i++) T[i][0] = T[i][1] = T[i][2] = T[i][3] = 0.f;
    uint32_t qd[8][4], held[2] = {0, 0};
    uint32_t qp = qa + 128 * 15, sta = st + 256 * 14;
    uint4* yd = ydst + 19 * 16;
#pragma unroll
    for (int i = 0; i < 6; i++) ldsm4(qd[i], qp - 16 * i);
    uint2 sv = lds64(sta + 256);
    float ci[4] = {bf_lo(sv.x), bf_hi(sv.x), bf_lo(sv.y), bf_hi(sv.y)};
    mbar_wait(BAR(MB_ZOK));
    TS(46);
#pragma unroll 2
    for (int be = 15; be >= 0; be--) {
#pragma unroll
      for (int k = 4; k >= 1; k--)
        mmac_p(be <= 15 - k, T[k], qd[0][0], qd[0][1], qd[0][2], qd[0][3], F[16 * k + 1], F[16 * k], T[k - 1]);
      mmac(T[0], qd[0][0], qd[0][1], qd[0][2], qd[0][3], F[1], F[0], ci);
      ldsm4(qd[6], qp - 16 * 6);
      ldsm4(qd[7], qp - 16 * 7);
      sv = lds64(sta);
#pragma unroll
      for (int i = 1; i < 8; i++) {
#pragma unroll
        for (int k = 3; k >= 0; k--)
          mma_p(k == 0 || be <= 15 - k, T[k], qd[i][0], qd[i][1], qd[i][2], qd[i][3], F[16 * k + 2 * i + 1], F[16 * k + 2 * i]);
        if (i < 7) ldsm4(qd[i - 1], qp - 128 - 16 * (i - 1));
        if (i == 2) {
          const uint32_t w0 = pack_bf(T[4][0], T[4][1]), w1 = pack_bf(T[4][2], T[4][3]);
          st_x_p(be <= 10 && !(be & 1), yd, nz(w0), w1, held[0], held[1]);
          held[0] = w0; held[1] = w1;
        }
        if (i == 4) {
          if (be <= 4) sv = make_uint2(0, 0);
          ci[0] = bf_lo(sv.x); ci[1] = bf_hi(sv.x); ci[2] = bf_lo(sv.y); ci[3] = bf_hi(sv.y);
        }
      }
      qp -= 128; sta -= 256; yd -= 16;
    }
#pragma unroll
    for (int B = 1; B >= 0; B--)
      st_x(ydst + B * 32, nz(pack_bf(T[2 * B][0], T[2 * B][1])), pack_bf(T[2 * B][2], T[2 * B][3]),
           pack_bf(T[2 * B + 1][0], T[2 * B + 1][1]), pack_bf(T[2 * B + 1][2], T[2 * B + 1][3]));
  }
}

__device__ __forceinline__ void feat(const float (&acc)[48], int j0, const uint32_t (&wf)[4], uint32_t* w) {
  const uint32_t a0 = pack_bf(acc[4 * j0], acc[4 * j0 + 1]), a1 = pack_bf(acc[4 * j0 + 2], acc[4 * j0 + 3]);
  const uint32_t a2 = pack_bf(acc[4 * j0 + 4], acc[4 * j0 + 5]), a3 = pack_bf(acc[4 * j0 + 6], acc[4 * j0 + 7]);
  float p[8];
  mma0(p[0], p[1], p[2], p[3], a0, a1, a2, a3, wf[0], wf[1]);
  mma0(p[4], p[5], p[6], p[7], a0, a1, a2, a3, wf[2], wf[3]);
  w[0] = pack_bf(p[0], p[2]); w[1] = pack_bf(p[1], p[3]); w[2] = pack_bf(p[4], p[6]); w[3] = pack_bf(p[5], p[7]);
}
__device__ __forceinline__ void dual_softmax(const uint32_t* w, uint32_t* e) {
  const float L = 1.44268798828125f;
  uint32_t mx = bmax2(bmax2(w[0], w[1]), bmax2(w[2], w[3]));
  uint32_t mn = bmin2(bmin2(w[0], w[1]), bmin2(w[2], w[3]));
  mx = bmax2(mx, __shfl_xor_sync(0xffffffffu, mx, 1));
  mn = bmin2(mn, __shfl_xor_sync(0xffffffffu, mn, 1));
  mx = bmax2(mx, __shfl_xor_sync(0xffffffffu, mx, 2));
  mn = bmin2(mn, __shfl_xor_sync(0xffffffffu, mn, 2));
  const float mx0 = bf_lo(mx) * -L, mx1 = bf_hi(mx) * -L, mn0 = bf_lo(mn) * L, mn1 = bf_hi(mn) * L;
  float ep[2][4], em[2][4];
#pragma unroll
  for (int i = 0; i < 4; i++) {
    const float x0 = bf_lo(w[i]), x1 = bf_hi(w[i]);
    ep[0][i] = ex2(fmaf(x0, L, mx0)); em[0][i] = ex2(fmaf(x0, -L, mn0));
    ep[1][i] = ex2(fmaf(x1, L, mx1)); em[1][i] = ex2(fmaf(x1, -L, mn1));
  }
  __half2 sp = __floats2half2_rn((ep[0][0] + ep[0][1]) + (ep[0][2] + ep[0][3]), (ep[1][0] + ep[1][1]) + (ep[1][2] + ep[1][3]));
  __half2 sm = __floats2half2_rn((em[0][0] + em[0][1]) + (em[0][2] + em[0][3]), (em[1][0] + em[1][1]) + (em[1][2] + em[1][3]));
  sp = __hadd2(sp, __shfl_xor_sync(0xffffffffu, sp, 1));
  sm = __hadd2(sm, __shfl_xor_sync(0xffffffffu, sm, 1));
  sp = __hadd2(sp, __shfl_xor_sync(0xffffffffu, sp, 2));
  sm = __hadd2(sm, __shfl_xor_sync(0xffffffffu, sm, 2));
  const float rp[2] = {rcp(__low2float(sp)), rcp(__high2float(sp))}, rm[2] = {rcp(__low2float(sm)), rcp(__high2float(sm))};
#pragma unroll
  for (int i = 0; i < 4; i++) {
    const int r = i & 1, k = i & 2;
    e[i] = pack_bf(ep[r][k] * rp[r], ep[r][k + 1] * rp[r]);
    e[4 + i] = pack_bf(em[r][k] * rm[r], em[r][k + 1] * rm[r]);
  }
}

__global__ void __launch_bounds__(NTHREADS, 1)
fused_kernel(const Params P, const __grid_constant__ CUtensorMap mx, const __grid_constant__ CUtensorMap mw,
             const __grid_constant__ CUtensorMap mo, const __grid_constant__ CUtensorMap mu,
             const __grid_constant__ CUtensorMap mout) {
  asm volatile("prefetch.tensormap [%0];" ::"l"(&mw) : "memory");
  asm volatile("prefetch.tensormap [%0];" ::"l"(&mx) : "memory");
  constexpr uint32_t sb = SB;
  const int tid = threadIdx.x, lane = tid & 31;
  const int warp = __shfl_sync(0xffffffffu, tid >> 5, 0);
  const int b = blockIdx.x, oct = b >> 3, i8 = b & 7;
  const int rt = oct < 8 ? oct : 15 - oct;
  const int hp = (oct >> 3) * 8 + i8;

  if (warp >= 12) asm volatile("setmaxnreg.dec.sync.aligned.u32 32;");
  if (warp == 12) {
    if (lane == 0) {
#pragma unroll
      for (int i = 0; i < 8; i++) mbar_init(BAR(MB_FULL + i), 1);
      asm volatile("fence.mbarrier_init.release.cluster;" ::: "memory");
    }
    __syncwarp();
    if (lane < 8) mbar_expect(BAR(MB_FULL) + 8 * lane, lane < 7 ? 28672 : 29696);
    __syncwarp();
    nb_arrive(NB_RDY, 256);
#pragma unroll 1
    for (int kb = 0; kb < 8; kb++) {
      e_tma3d(sb + OFF_W + kb * 12288, &mw, BAR(MB_FULL) + 8 * kb, hp * 32, kb * 64, 0);
      if (kb < 5) e_tma2d(sb + OFF_X + (kb < 2 ? kb + 3 : kb - 2) * 16384, &mx, BAR(MB_FULL) + 8 * kb, kb * 64, rt * 256);
    }
    e_prefetch(P.x + (size_t)(rt * 256 + hp * 8) * 512, 8192);
    e_bulk(sb + OFF_PHI, P.wphi + hp * 512, 1024, BAR(MB_FULL + 7));
    if (smem_u32(smem_raw) != SB) __trap();
  }
  if (warp >= 12) {
    if (warp == 12) {
      nb_sync(NB_PROD, 64);
      if (STEP_U < 0) e_tma5d(sb + OFF_STG0, &mu, BAR(MB_URAW), i8 * 64, oct * 4);
      uint32_t slot = sb + OFF_X + 3 * 16384;
#pragma unroll 1
      for (int n = 0; n < 11; n++) {
        mbar_wait(BAR(MB_EMPTY) + 8 * n);
        const int m = n + 5;
        e_tma2d(slot, &mx, BAR(MB_FULL) + 8 * m, (m & 7) * 64, rt * 256 + (m >> 3) * 128);
        slot = slot == sb + OFF_X + 4 * 16384 ? sb + OFF_X : slot + 16384;
        if (n == STEP_PF) e_prefetch(P.x + (size_t)(rt * 256 + 128 + hp * 8) * 512, 8192);
        if (n == STEP_U) e_tma5d(sb + OFF_STG0, &mu, BAR(MB_URAW), i8 * 64, oct * 4);
        if (n == 7) e_prefetch(P.wo + (size_t)b * 2048, 4096);
      }
#pragma unroll 1
      for (int i = 0; i < 8; i++) {
        mbar_wait(BAR(MB_EMPTY + 10) + 8 * ((0x54332100u >> (4 * i)) & 7));
        const int w0 = (0x54736210u >> (4 * i)) & 7;
        const int col = (hp & 3) * 128 + (w0 >> 2) * 64;
        e_tma2d(sb + OFF_W + w0 * 16384, &mo, BAR(MB_WO) + 8 * (w0 >> 2), col, w0 * 64);
        e_tma2d(sb + OFF_W + w0 * 16384 + 8192, &mo, BAR(MB_WO) + 8 * (w0 >> 2), col ^ 64, w0 * 64);
      }
    } else {
      if (warp == 13) {
        if (lane == 0) {
#pragma unroll
          for (int i = 8; i < 39; i++) mbar_init(BAR(i), i < MB_EMPTY ? 1 : (i < MB_RAWDONE ? 4 : (i == MB_RAWDONE ? 3 : 12)));
          asm volatile("fence.mbarrier_init.release.cluster;" ::: "memory");
        }
        __syncwarp();
        if (lane < 11) mbar_expect(BAR(MB_FULL + 8) + 8 * lane, lane < 9 ? 16384 : 65536);
        __syncwarp();
        nb_arrive(NB_PROD, 64);
        nb_arrive(NB_PREP, 288);
      }
      nb_sync(NB_RDY, 256);
      const unsigned cnt0 = ld_x32(g_cnt + 256);
      mbar_wait(BAR(MB_URAW));
      if (tid == 416) TS1(48);
      uint4* dst = g_uT + (size_t)(i8 * 64 + (lane >> 2)) * 256 + (lane & 1) * 128 + oct * 8 + ((lane >> 1) & 1);
#pragma unroll 1
      for (int i = warp - 13; i < 32; i += 3) {
        uint32_t r[4];
        ldsm4t(r, sb + OFF_STG0 + (i >> 3) * 4096 + lane * 128 + (((i ^ lane) & 7) << 4));
        dst[(i & 7) * 2048 + (i >> 3) * 2] = make_uint4(r[0], r[1], r[2], r[3]);
      }
      if (lane == 0) mbar_arrive(BAR(MB_RAWDONE));
      nb_sync(NB_INIT, 96);
      if (warp > 13) {
        mbar_wait(BAR(MB_EMPTY + ZERO_STEP));
        uint4* po = g_o + (size_t)(rt * 4 * 32 + hp * 2) * 128;
        uint4* py = g_y + (size_t)b * 1024;
        uint4* pp = g_part + (size_t)(hp * 8 + rt) * 144;
#pragma unroll 1
        for (int i = tid - 448; i < ZERO_N; i += 64) {
          st_x(po + (i >> 8) * 4096 + (i & 255), 0, 0, 0, 0);
          st_x(py + i, 0, 0, 0, 0);
          if (i < 144) st_x(pp + i, 0, 0, 0, 0);
        }
        nb_sync(NB_ZERO, 64);
        if (warp == 15) return;
      }
      if (lane == 0) TS1(warp == 13 ? 49 : 55);
      if (lane == 0)
        asm volatile("red.release.gpu.global.add.u32 [%0], %1;" ::"l"(g_cnt + (warp == 13 ? i8 : 8) * 32), "r"(warp == 13 ? 8 : 1) : "memory");
      if (lane == 0) TS1(warp == 13 ? 50 : 56);
#pragma unroll 1
      for (int i = 0; i < SPIN_MAX; i++) {
        unsigned v;
        asm volatile("ld.acquire.gpu.global.u32 %0, [%1];" : "=r"(v) : "l"(g_cnt + (warp == 13 ? b >> 4 : 8) * 32) : "memory");
        if ((int)(v - ((cnt0 & ~(unsigned)(NCTA - 1)) + NCTA)) >= 0) break;
      }
      if (lane == 0) TS1(warp == 13 ? 51 : 57);
      if (warp == 14) {
        if (lane == 0) mbar_arrive(BAR(MB_ZOK));
      } else {
        mbar_wait(BAR(MB_EMPTY + 11));
        sts128(sb + OFF_U + (lane >> 4) * U_CH + ((lane >> 3) & 1) * U_ODD + (lane & 7) * 16, 0, 0, 0, 0);
        sts128(sb + OFF_U + (2 + (lane >> 4)) * U_CH + ((lane >> 3) & 1) * U_ODD + (lane & 7) * 16, 0, 0, 0, 0);
        asm volatile("fence.proxy.async.global;" ::: "memory");
        __syncwarp();
        e_expect(BAR(MB_UFULL), 16384);
#pragma unroll 1
        for (int i = 0; i < 8; i++)
          e_bulk(sb + OFF_U + (i >> 1) * U_CH + (i & 1) * U_ODD + U_PAD, g_uT + (size_t)(b * 8 + i) * 128, 2048, BAR(MB_UFULL));
      }
    }
    return;
  }

  asm volatile("setmaxnreg.inc.sync.aligned.u32 160;");
  const int wg = warp >> 2, w = warp & 3, t = tid & 127;
  const int g = lane >> 2, c = lane & 3;
  const uint32_t tb = sb + OFF_T + w * T_CH;
  const int d = b * 4 + w;
  if (wg != 0) {
    const unsigned short dsk = __ldg((const unsigned short*)P.Dskip + d);
    float k[5][4], k2048 = 0.f, dt;
#pragma unroll
    for (int j = 0; j < 5; j++) k[j][0] = k[j][1] = k[j][2] = k[j][3] = 0.f;
#pragma unroll 1
    for (int r = 0; r < wg; r++) {
      kgen_round(P, d, r ? 96 : (wg - 1) * 48, r ? 4 : 6, lane, dt, BAR(MB_EMPTY + 7) + 64 * r, k, k2048);
      if (r == 0 && lane == 0 && (fu(k[0][0]) & fu(k[1][0]) & fu(k[2][0]) & fu(k[3][0]) & fu(k[4][0])) != 0xffffffffu)
        mbar_arrive(BAR(MB_CLOSE));
    }
    k2048 += __shfl_xor_sync(0xffffffffu, k2048, 1);
    k2048 += __shfl_xor_sync(0xffffffffu, k2048, 2);
    if (wg == 2) {
      TS(34);
      nb_sync(NB_KPART, 256);
      const float sc = 2.f * dt;
#pragma unroll
      for (int j = 0; j < 5; j++) {
        const uint4 v = lds128(tb + j * 512 + lane * 16);
        k[j][0] = (k[j][0] + uf(v.x)) * sc; k[j][1] = (k[j][1] + uf(v.y)) * sc;
        k[j][2] = (k[j][2] + uf(v.z)) * sc; k[j][3] = (k[j][3] + uf(v.w)) * sc;
      }
      k2048 = (k2048 + uf(lds32(tb + 2560))) * sc;
      if (lane == 0) k[0][0] += bf_lo(dsk);
      __syncwarp();
      build_tables(tb, lane, k, k2048);
      TS(35);
      mbar_wait(BAR(MB_UFULL));
      conv_channel(sb + OFF_U + w * U_CH, tb, lane, g_y + (size_t)d * 256 + lane);
      nb_arrive(NB_BDONE, 384);
      TS(37);
      const int lam = w * 8 + g;
      const uint4* src = g_y + (size_t)(oct * 32 + c * 8) * 256 + i8 * 32 + lam;
      uint4 v[8];
#pragma unroll 1
      for (int it = 0; it < SPIN_MAX; it++) {
        uint32_t m = 0xffffffffu;
#pragma unroll
        for (int i = 0; i < 8; i++) v[i] = ld_x(src + i * 256);
#pragma unroll
        for (int i = 0; i < 8; i++) m = min(m, v[i].x);
        if (__all_sync(0xffffffffu, m != 0)) break;
      }
      __nv_bfloat16* dst = P.out + (size_t)(i8 * 256 + (lam >> 2) * 16 + (lam & 3) * 2) * 1024 + 512 + oct * 32 + c * 8;
#pragma unroll
      for (int i = 0; i < 8; i++) *(uint4*)(dst + (size_t)((i >> 2) * 128 + ((i >> 1) & 1) * 8 + (i & 1)) * 1024) = tr_row(v, i);
      TS(38);
      GT(63);
      return;
    }
#pragma unroll
    for (int j = 0; j < 5; j++) sts128(tb + j * 512 + lane * 16, fu(k[j][0]), fu(k[j][1]), fu(k[j][2]), fu(k[j][3]));
    if (lane == 0) sts32(tb + 2560, fu(k2048));
    nb_arrive(NB_KPART, 256);
    mbar_wait(BAR(MB_CLOSE));
    TS(30);
  } else {
    nb_sync(NB_RDY, 256);
    TS(0);
  }

  float acc[2][48];
  {
    uint32_t fb = BAR(MB_FULL) + 64 * wg;
    uint32_t da = (uint32_t)mkdesc(sb + OFF_X, 16, 0, 0) + (wg ? 1024 : 3072), db = (uint32_t)mkdesc(sb + OFF_W, 4096, 0, 0);
    constexpr uint64_t ha = mkdesc(0, 0, 1024, 1), hb = mkdesc(0, 0, 512, 2);
#pragma unroll 1
    for (int kb = 0; kb < 8; kb++) {
      mbar_wait(fb);
      if (kb == 0) TS(wg * 16 + 2);
      WG_FENCE();
#pragma unroll
      for (int k = 0; k < 4; k++) {
        wgmma_ss_n96(acc[0], ha | (da + 2 * k), hb | (db + 64 * k), k ? 1 : kb);
        wgmma_ss_n96(acc[1], ha | (da + 2 * k + 512), hb | (db + 64 * k), k ? 1 : kb);
      }
      WG_COMMIT();
      WG_WAIT(1);
      if (kb > 0 && lane == 0) mbar_arrive(fb + 8 * (MB_EMPTY - MB_FULL - 1));
      fb += 8; db += 768;
      da = da == (uint32_t)mkdesc(sb + OFF_X + 65536, 16, 0, 0) ? da - 4096 : da + 1024;
    }
    WG_WAIT(0);
    if (lane == 0) mbar_arrive(fb + 8 * (MB_EMPTY - MB_FULL - 1));
    mbar_wait(fb + 8 * (MB_EMPTY - MB_FULL - 1));
  }
  uint32_t wf[2][4];
  ldsm4t(wf[0], sb + OFF_PHI + (lane & 15) * 32 + (lane >> 4) * 16);
  ldsm4t(wf[1], sb + OFF_PHI + 512 + (lane & 15) * 32 + (lane >> 4) * 16);
  TS(wg * 16 + 3);

  uint32_t pw[32], eq[32];
#pragma unroll
  for (int u = 0; u < 4; u++)
#pragma unroll
    for (int h = 0; h < 2; h++) feat(acc[u & 1], (u < 2 ? 4 : 0) + 2 * h, wf[h], pw + 8 * u + 4 * h);
  {
    uint32_t all = 0xffffffffu;
#pragma unroll
    for (int i = 0; i < 16; i++) all &= pw[2 * i];
    if (wg == 0 && lane == 0 && all != 0xffffffffu) mbar_arrive(BAR(MB_CLOSE));
  }
  mbar_wait(BAR(MB_RAWDONE));
  const uint32_t stg0 = sb + OFF_STG0, stg1 = sb + OFF_X + 32768;
  uint32_t sl = (wg ? stg1 : stg0) + w * 3072 + lane * 16;
#pragma unroll
  for (int mt = 0; mt < 2; mt++)
#pragma unroll
    for (int h = 0; h < 2; h++) {
      const float* a = acc[mt] + 32 + 8 * h;
      stsm4(sl + mt * 12288 + 2048 + h * 512, pack_bf(a[0], a[1]), pack_bf(a[2], a[3]), pack_bf(a[4], a[5]), pack_bf(a[6], a[7]));
    }
#pragma unroll 1
  for (int u = 0; u < 4; u++) {
#pragma unroll
    for (int i = 0; i < 16; i++) eq[i] = eq[16 + i];
    dual_softmax(pw, eq + 16);
    dual_softmax(pw + 4, eq + 24);
    if (u < 2) {
#pragma unroll
      for (int i = 0; i < 4; i++) stsm4(sl + i * 512, eq[16 + 4 * i], eq[17 + 4 * i], eq[18 + 4 * i], eq[19 + 4 * i]);
      if (wg) nb_arrive(NB_ST0 + u, 256);
      sl += 12288;
    }
#pragma unroll
    for (int i = 0; i < 24; i++) pw[i] = pw[i + 8];
  }
  TS(wg * 16 + 4);
  const uint32_t kvs = stg0;
  if (wg == 0) {
    nb_sync(NB_WG0, 128);
    mbar_wait(BAR(MB_ZOK));
    mbar_wait(BAR(MB_EMPTY + 15));
    float kv[12];
#pragma unroll
    for (int i = 0; i < 12; i++) kv[i] = 0.f;
    const int mi = lane >> 3;
    const uint32_t ao = w * 512 + (lane & 7) * 16 + ((mi & 1) * 2 + (mi >> 1)) * 128, bo = 2048 + (w >> 1) * 512 + lane * 16;
#pragma unroll 1
    for (int j = 0; j < 4; j++) {
      if (j >= 2) nb_sync(NB_ST0 + j - 2, 256);
      const uint32_t sg = (j >= 2 ? stg1 : stg0) + (j & 1) * 12288;
      uint32_t a[4][4], bb[4][4];
#pragma unroll
      for (int s = 0; s < 4; s++) { ldsm4t(a[s], sg + s * 3072 + ao); ldsm4t(bb[s], sg + s * 3072 + bo); }
#pragma unroll
      for (int s = 0; s < 4; s++) {
        mma(kv[0], kv[1], kv[2], kv[3], a[s][0], a[s][1], a[s][2], a[s][3], bb[s][0], bb[s][1]);
        mma(kv[4], kv[5], kv[6], kv[7], a[s][0], a[s][1], a[s][2], a[s][3], bb[s][2], bb[s][3]);
        mma(kv[8], kv[9], kv[10], kv[11], a[s][0], a[s][1], a[s][2], a[s][3], 0x3F803F80u, 0x3F803F80u);
      }
    }
    uint4* pp = g_part + (size_t)(hp * 8 + rt) * 144;
    st_x(pp + t, nz(pack_bf(kv[0], kv[1])), pack_bf(kv[2], kv[3]), pack_bf(kv[4], kv[5]), pack_bf(kv[6], kv[7]));
    if (c < 2) st_x32((uint32_t*)(pp + 128) + w * 16 + c * 8 + g, nz(fu(c ? kv[10] : kv[8])));
    TS(5);
    const uint4* ps = g_part + (size_t)hp * 8 * 144 + t;
    const uint32_t* zs = (const uint32_t*)(g_part + (size_t)(hp * 8 + (lane >> 4) * 4) * 144 + 128) + w * 16 + (lane & 15);
    uint4 v[8];
    uint32_t zv[4];
#pragma unroll 1
    for (int it = 0; it < SPIN_MAX; it++) {
#pragma unroll
      for (int i = 0; i < 8; i++) v[i] = ld_x(ps + i * 144);
#pragma unroll
      for (int i = 0; i < 4; i++) zv[i] = ld_x32(zs + i * 576);
      uint32_t m = min(min(zv[0], zv[1]), min(zv[2], zv[3]));
#pragma unroll
      for (int i = 0; i < 8; i++) m = min(m, v[i].x);
      if (__all_sync(0xffffffffu, m != 0)) break;
    }
    float s4[4][4];
#pragma unroll
    for (int i = 0; i < 4; i++) s4[i][0] = s4[i][1] = s4[i][2] = s4[i][3] = 0.f;
    const uint32_t eye = (g >> 1) == c ? ((g & 1) ? 0x3F800000u : 0x3F80u) : 0u;
#pragma unroll
    for (int r = 0; r < 8; r++) {
      mma_k8(s4[(r & 1) * 2], v[r].x, v[r].y, eye);
      mma_k8(s4[(r & 1) * 2 + 1], v[r].z, v[r].w, eye);
    }
    float s[8];
#pragma unroll
    for (int i = 0; i < 8; i++) s[i] = s4[i >> 2][i & 3] + s4[2 + (i >> 2)][i & 3];
    float zsum = (uf(zv[0]) + uf(zv[1])) + (uf(zv[2]) + uf(zv[3]));
    zsum += __shfl_xor_sync(0xffffffffu, zsum, 16);
    stsm4(kvs + w * 512 + lane * 16, pack_bf(s[0], s[1]), pack_bf(s[2], s[3]), pack_bf(s[4], s[5]), pack_bf(s[6], s[7]));
    if (lane < 16) sts16(kvs + 2048 + (w * 16 + lane) * 2, pack_bf(zsum, 0.f));
    TS(6);
  }
  nb_sync(NB_KV, 256);
  {
    uint32_t kb_[4][4], zb[8];
#pragma unroll
    for (int i = 0; i < 4; i++) ldsm4t(kb_[i], kvs + i * 512 + lane * 16);
#pragma unroll
    for (int i = 0; i < 8; i++) zb[i] = lds32(kvs + 2048 + i * 16 + c * 4);
    uint4* od = g_o + (size_t)((rt * 4 + wg * 2) * 32 + hp * 2) * 128 + t;
#pragma unroll 1
    for (int mt = 0; mt < 2; mt++) {
#pragma unroll
      for (int h = 0; h < 2; h++) {
        const uint32_t* e = eq + 8 * h;
        float n[8], dn[4];
        mma0(dn[0], dn[1], dn[2], dn[3], e[0], e[1], e[2], e[3], zb[4 * h], zb[4 * h + 1]);
        mma0(n[0], n[1], n[2], n[3], e[0], e[1], e[2], e[3], kb_[2 * h][0], kb_[2 * h][1]);
        mma0(n[4], n[5], n[6], n[7], e[0], e[1], e[2], e[3], kb_[2 * h][2], kb_[2 * h][3]);
        mma(dn[0], dn[1], dn[2], dn[3], e[4], e[5], e[6], e[7], zb[4 * h + 2], zb[4 * h + 3]);
        mma(n[0], n[1], n[2], n[3], e[4], e[5], e[6], e[7], kb_[2 * h + 1][0], kb_[2 * h + 1][1]);
        mma(n[4], n[5], n[6], n[7], e[4], e[5], e[6], e[7], kb_[2 * h + 1][2], kb_[2 * h + 1][3]);
        const float r0 = rcp(dn[0] + 1e-6f), r1 = rcp(dn[2] + 1e-6f);
        st_x(od + h * 128, nz(pack_bf(n[0] * r0, n[1] * r0)), pack_bf(n[2] * r1, n[3] * r1), pack_bf(n[4] * r0, n[5] * r0),
             pack_bf(n[6] * r1, n[7] * r1));
      }
#pragma unroll
      for (int i = 0; i < 16; i++) eq[i] = eq[16 + i];
      od += 4096;
    }
  }
  TS(wg * 16 + 7);
  const int rb = rt * 4 + (hp >> 2);
  const uint4* osrc = g_o + (size_t)(rb * 32 + wg * 16) * 128 + t;
  uint4 af[16];
  {
    const uint32_t* probe = (const uint32_t*)(osrc - lane + (lane & 15) * 128 + (lane >> 4) * 31);
#pragma unroll 1
    for (int it = 0; it < SPIN_MAX; it++) {
      uint32_t m = ld_x32(probe);
#pragma unroll
      for (int i = 0; i < 4; i++) af[i] = ld_x(osrc + i * 128);
#pragma unroll
      for (int i = 0; i < 4; i++) m = min(m, af[i].x);
      if (__all_sync(0xffffffffu, m != 0)) break;
    }
  }
#pragma unroll
  for (int i = 4; i < 16; i++) af[i] = ld_x(osrc + i * 128);
  TS(wg * 16 + 8);
  mbar_wait(BAR(MB_WO) + 8 * wg);
  nb_sync(NB_BDONE, 384);
  TS(wg * 16 + 9);
  float oc[64];
  {
    const uint64_t db = mkdesc(sb + OFF_W, 8192, 1024, 1) + wg * 4096;
#pragma unroll
    for (int j = 0; j < 4; j++) {
      if (j) {
#pragma unroll 1
        for (int it = 0; it < SPIN_MAX; it++) {
          const uint32_t m = min(min(af[4 * j].x, af[4 * j + 1].x), min(af[4 * j + 2].x, af[4 * j + 3].x));
          if (__all_sync(0xffffffffu, m != 0)) break;
#pragma unroll
          for (int i = 0; i < 4; i++) af[4 * j + i] = ld_x(osrc + (4 * j + i) * 128);
        }
      }
      WG_FENCE();
#pragma unroll
      for (int k = 0; k < 4; k++) wgmma_rs_n128(oc, af[4 * j + k], db + 128 * k + 1024 * j, j | k);
    }
    WG_COMMIT();
    WG_WAIT(0);
  }
  TS(wg * 16 + 10);
  const uint32_t xo = stg1 + wg * 16384 + t * 16, xi = stg1 + (wg ^ 1) * 16384 + t * 16;
#pragma unroll
  for (int i = 0; i < 8; i++) sts128(xo + i * 2048, fu(oc[32 + 4 * i]), fu(oc[33 + 4 * i]), fu(oc[34 + 4 * i]), fu(oc[35 + 4 * i]));
  nb_sync(NB_RED, 256);
  const uint32_t ot = stg0 + warp * 2048;
#pragma unroll
  for (int i = 0; i < 8; i += 2) {
    const uint4 v0 = lds128(xi + i * 2048), v1 = lds128(xi + i * 2048 + 2048);
    stsm4(ot + (lane & 15) * 128 + (((i + (lane >> 4)) ^ (lane & 7)) << 4),
          pack_bf(oc[4 * i] + uf(v0.x), oc[4 * i + 1] + uf(v0.y)), pack_bf(oc[4 * i + 2] + uf(v0.z), oc[4 * i + 3] + uf(v0.w)),
          pack_bf(oc[4 * i + 4] + uf(v1.x), oc[4 * i + 5] + uf(v1.y)), pack_bf(oc[4 * i + 6] + uf(v1.z), oc[4 * i + 7] + uf(v1.w)));
  }
  asm volatile("fence.proxy.async.shared::cta;" ::: "memory");
  __syncwarp();
  e_store2d(&mout, ot, (hp & 3) * 128 + wg * 64, rb * 64 + w * 16);
  TS(wg * 16 + 11);
  GT(61 + wg);
}

typedef CUresult (*EncodeFn)(CUtensorMap*, CUtensorMapDataType, cuuint32_t, void*, const cuuint64_t*, const cuuint64_t*,
                             const cuuint32_t*, const cuuint32_t*, CUtensorMapInterleave, CUtensorMapSwizzle,
                             CUtensorMapL2promotion, CUtensorMapFloatOOBfill);

}

extern "C" void kernel_launch(void* const* d_in, const int* in_sizes, int n_in, void* d_out, int out_size) {
  (void)in_sizes; (void)n_in; (void)out_size;
  void* fn = nullptr;
  cudaDriverEntryPointQueryResult qr;
  cudaGetDriverEntryPoint("cuTensorMapEncodeTiled", &fn, cudaEnableDefault, &qr);
  EncodeFn enc = (EncodeFn)fn;
  CUtensorMap mx, mw, mo, mu, mout;
  const cuuint32_t es[5] = {1, 1, 1, 1, 1};
  {
    cuuint64_t dims[2] = {512, 2048}, st[1] = {1024};
    cuuint32_t box[2] = {64, 128};
    enc(&mx, CU_TENSOR_MAP_DATA_TYPE_BFLOAT16, 2, d_in[0], dims, st, box, es, CU_TENSOR_MAP_INTERLEAVE_NONE,
        CU_TENSOR_MAP_SWIZZLE_128B, CU_TENSOR_MAP_L2_PROMOTION_L2_128B, CU_TENSOR_MAP_FLOAT_OOB_FILL_NONE);
  }
  {
    cuuint64_t dims[3] = {512, 512, 3}, st[2] = {3072, 1024};
    cuuint32_t box[3] = {32, 64, 3};
    enc(&mw, CU_TENSOR_MAP_DATA_TYPE_BFLOAT16, 3, d_in[1], dims, st, box, es, CU_TENSOR_MAP_INTERLEAVE_NONE,
        CU_TENSOR_MAP_SWIZZLE_64B, CU_TENSOR_MAP_L2_PROMOTION_L2_128B, CU_TENSOR_MAP_FLOAT_OOB_FILL_NONE);
  }
  {
    cuuint64_t dims[2] = {512, 512}, st[1] = {1024};
    cuuint32_t box[2] = {64, 64};
    enc(&mo, CU_TENSOR_MAP_DATA_TYPE_BFLOAT16, 2, d_in[3], dims, st, box, es, CU_TENSOR_MAP_INTERLEAVE_NONE,
        CU_TENSOR_MAP_SWIZZLE_128B, CU_TENSOR_MAP_L2_PROMOTION_L2_128B, CU_TENSOR_MAP_FLOAT_OOB_FILL_NONE);
  }
  {
    cuuint64_t dims[5] = {512, 2, 4, 4, 64}, st[4] = {1024, 8192, 2048, 32768};
    cuuint32_t box[5] = {64, 2, 4, 4, 4};
    enc(&mu, CU_TENSOR_MAP_DATA_TYPE_BFLOAT16, 5, d_in[4], dims, st, box, es, CU_TENSOR_MAP_INTERLEAVE_NONE,
        CU_TENSOR_MAP_SWIZZLE_128B, CU_TENSOR_MAP_L2_PROMOTION_L2_128B, CU_TENSOR_MAP_FLOAT_OOB_FILL_NONE);
  }
  {
    cuuint64_t dims[2] = {1024, 2048}, st[1] = {2048};
    cuuint32_t box[2] = {64, 16};
    enc(&mout, CU_TENSOR_MAP_DATA_TYPE_BFLOAT16, 2, d_out, dims, st, box, es, CU_TENSOR_MAP_INTERLEAVE_NONE,
        CU_TENSOR_MAP_SWIZZLE_128B, CU_TENSOR_MAP_L2_PROMOTION_NONE, CU_TENSOR_MAP_FLOAT_OOB_FILL_NONE);
  }
  Params P;
  P.x = (const __nv_bfloat16*)d_in[0];
  P.wphi = (const __nv_bfloat16*)d_in[2];
  P.wo = (const __nv_bfloat16*)d_in[3];
  P.u = (const __nv_bfloat16*)d_in[4];
  P.logA = (const __nv_bfloat16*)d_in[5];
  P.Aim = (const __nv_bfloat16*)d_in[6];
  P.Cre = (const __nv_bfloat16*)d_in[7];
  P.Cim = (const __nv_bfloat16*)d_in[8];
  P.logdt = (const __nv_bfloat16*)d_in[9];
  P.Dskip = (const __nv_bfloat16*)d_in[10];
  P.out = (__nv_bfloat16*)d_out;
  cudaFuncSetAttribute(fused_kernel, cudaFuncAttributeMaxDynamicSharedMemorySize, SMEM_BYTES);
  fused_kernel<<<NCTA, NTHREADS, SMEM_BYTES>>>(P, mx, mw, mo, mu, mout);
}
```

```cpp
#include <cuda_runtime.h>
#include <cuda_bf16.h>
#include <cuda_fp16.h>
#include <cuda.h>
#include <stdint.h>

#define DBG_TS 0

namespace {

constexpr int NTHREADS = 512;
constexpr int NCTA = 128;
constexpr int OFF_W = 0;
constexpr int OFF_X = 98304;
constexpr int OFF_U = OFF_X + 65536;
constexpr int U_CH = 4416, U_ODD = 2240, U_PAD = 128;
constexpr int OFF_STG0 = OFF_U + 18432;
constexpr int OFF_T = OFF_STG0 + 24576;
constexpr int T_CH = 5216;
constexpr int T_D = 0;
constexpr int T_5 = 2144;
constexpr int T_3 = T_5 + 384;
constexpr int T_7 = T_5 + 1024;
constexpr int T_9 = T_7 + 320;
constexpr int T_KC = T_9 + 320;
constexpr int T_ST = T_5 - 1024;
constexpr int OFF_PHI = OFF_T + 4 * T_CH;
constexpr int OFF_BAR = OFF_PHI + 1024;
constexpr int SMEM_BYTES = OFF_BAR + 512;
constexpr uint32_t SB = 1024;
static_assert(T_KC + 2 * 656 <= T_CH, "table size");
static_assert(SMEM_BYTES <= 232448, "smem");
constexpr int MB_FULL = 0  , MB_URAW = 16, MB_WO = 17  , MB_UFULL = 19, MB_ZOK = 20,
              MB_EMPTY = 21  , MB_KREAD = 37, MB_RAWDONE = 38, MB_CLOSE = 39;
__host__ __device__ constexpr uint32_t BAR(int i) { return SB + OFF_BAR + 8 * i; }
constexpr int NB_WG0 = 1, NB_KPART = 2, NB_ST0 = 3  , NB_KV = 5, NB_RED = 6, NB_INIT = 7, NB_PREP = 8, NB_PROD = 9, NB_RDY = 10, NB_BDONE = 11, NB_ZERO = 12;
#define ZERO_N 1024
#define ZERO_STEP 7
#define STEPU 0
#define STEPPF 0
constexpr int STEP_PF = STEPPF, STEP_U = STEPU;
constexpr int SPIN_MAX = 1 << 16;

__device__ unsigned g_cnt[9 * 32];
__device__ uint4 g_uT[512 * 256];
__device__ uint4 g_part[16 * 8 * 144];
__device__ uint4 g_o[32 * 32 * 128];
__device__ uint4 g_y[512 * 8 * 32];
extern __shared__ uint8_t smem_raw[];
#define TS(i) do {} while (0)
#define TS1(i) do {} while (0)
#define GT(i) do {} while (0)

__device__ __forceinline__ uint32_t smem_u32(const void* p) { return (uint32_t)__cvta_generic_to_shared(p); }
__device__ __forceinline__ void mbar_arrive(uint32_t b) {
  asm volatile("mbarrier.arrive.shared::cta.b64 _, [%0];" ::"r"(b) : "memory");
}
__device__ __forceinline__ void mbar_wait(uint32_t b) {
  uint32_t done = 0;
#pragma unroll 1
  for (int i = 0; i < SPIN_MAX && !done; i++) {
    asm volatile("{\n.reg .pred p;\nmbarrier.try_wait.parity.shared::cta.b64 p, [%1], 0, 4000;\nselp.u32 %0, 1, 0, p;\n}\n"
                 : "=r"(done) : "r"(b) : "memory");
  }
}
__device__ __forceinline__ void mbar_init(uint32_t b, int n) {
  asm volatile("mbarrier.init.shared::cta.b64 [%0], %1;" ::"r"(b), "r"(n) : "memory");
}
__device__ __forceinline__ void mbar_expect(uint32_t b, int bytes) {
  asm volatile("mbarrier.arrive.expect_tx.shared::cta.b64 _, [%0], %1;" ::"r"(b), "r"(bytes) : "memory");
}
__device__ __forceinline__ void nb_sync(int id, int n) { asm volatile("bar.sync %0, %1;" ::"r"(id), "r"(n) : "memory"); }
__device__ __forceinline__ void nb_arrive(int id, int n) { asm volatile("bar.arrive %0, %1;" ::"r"(id), "r"(n) : "memory"); }
#define ELECT "{\n.reg .pred p;\nelect.sync _|p, 0xffffffff;\n@p "
__device__ __forceinline__ void e_expect(uint32_t b, int bytes) {
  asm volatile(ELECT "mbarrier.arrive.expect_tx.shared::cta.b64 _, [%0], %1;\n}\n" ::"r"(b), "r"(bytes) : "memory");
}
__device__ __forceinline__ void e_tma2d(uint32_t dst, const CUtensorMap* m, uint32_t bar, int c0, int c1) {
  asm volatile(ELECT "cp.async.bulk.tensor.2d.shared::cluster.global.mbarrier::complete_tx::bytes [%0], [%1, {%3,%4}], [%2];\n}\n"
               ::"r"(dst), "l"(m), "r"(bar), "r"(c0), "r"(c1) : "memory");
}
__device__ __forceinline__ void e_tma3d(uint32_t dst, const CUtensorMap* m, uint32_t bar, int c0, int c1, int c2) {
  asm volatile(ELECT "cp.async.bulk.tensor.3d.shared::cluster.global.mbarrier::complete_tx::bytes [%0], [%1, {%3,%4,%5}], [%2];\n}\n"
               ::"r"(dst), "l"(m), "r"(bar), "r"(c0), "r"(c1), "r"(c2) : "memory");
}
__device__ __forceinline__ void e_tma5d(uint32_t dst, const CUtensorMap* m, uint32_t bar, int c0, int c4) {
  asm volatile(ELECT "cp.async.bulk.tensor.5d.shared::cluster.global.mbarrier::complete_tx::bytes [%0], [%1, {%3,%5,%5,%5,%4}], [%2];\n}\n"
               ::"r"(dst), "l"(m), "r"(bar), "r"(c0), "r"(c4), "r"(0) : "memory");
}
__device__ __forceinline__ void e_bulk(uint32_t dst, const void* src, int bytes, uint32_t bar) {
  asm volatile(ELECT "cp.async.bulk.shared::cluster.global.mbarrier::complete_tx::bytes [%0], [%1], %2, [%3];\n}\n"
               ::"r"(dst), "l"(src), "r"(bytes), "r"(bar) : "memory");
}
__device__ __forceinline__ void e_prefetch(const void* p, int bytes) {
  asm volatile(ELECT "cp.async.bulk.prefetch.L2.global [%0], %1;\n}\n" ::"l"(p), "r"(bytes) : "memory");
}
__device__ __forceinline__ void e_store2d(const CUtensorMap* m, uint32_t src, int c0, int c1) {
  asm volatile(ELECT "cp.async.bulk.tensor.2d.global.shared::cta.bulk_group [%0, {%2,%3}], [%1];\n"
               "@p cp.async.bulk.commit_group;\n@p cp.async.bulk.wait_group.read 0;\n}\n"
               ::"l"(m), "r"(src), "r"(c0), "r"(c1) : "memory");
}
__host__ __device__ constexpr uint64_t mkdesc(uint32_t addr, uint32_t lbo, uint32_t sbo, int swz) {
  return (uint64_t)((addr & 0x3FFFF) >> 4) | ((uint64_t)(lbo >> 4) << 16) | ((uint64_t)(sbo >> 4) << 32) |
         ((uint64_t)swz << 62);
}
#define WG_FENCE() asm volatile("wgmma.fence.sync.aligned;" ::: "memory")
#define WG_COMMIT() asm volatile("wgmma.commit_group.sync.aligned;" ::: "memory")
#define WG_WAIT(n) asm volatile("wgmma.wait_group.sync.aligned " #n ";" ::: "memory")

__device__ __forceinline__ void mma(float& d0, float& d1, float& d2, float& d3, uint32_t a0, uint32_t a1, uint32_t a2,
                                    uint32_t a3, uint32_t b0, uint32_t b1) {
  asm volatile("mma.sync.aligned.m16n8k16.row.col.f32.bf16.bf16.f32 {%0,%1,%2,%3},{%4,%5,%6,%7},{%8,%9},{%0,%1,%2,%3};"
               : "+f"(d0), "+f"(d1), "+f"(d2), "+f"(d3)
               : "r"(a0), "r"(a1), "r"(a2), "r"(a3), "r"(b0), "r"(b1));
}
__device__ __forceinline__ void mmac(float (&d)[4], uint32_t a0, uint32_t a1, uint32_t a2, uint32_t a3, uint32_t b0,
                                     uint32_t b1, const float (&c)[4]) {
  asm volatile("mma.sync.aligned.m16n8k16.row.col.f32.bf16.bf16.f32 {%0,%1,%2,%3},{%4,%5,%6,%7},{%8,%9},{%10,%11,%12,%13};"
               : "=f"(d[0]), "=f"(d[1]), "=f"(d[2]), "=f"(d[3])
               : "r"(a0), "r"(a1), "r"(a2), "r"(a3), "r"(b0), "r"(b1), "f"(c[0]), "f"(c[1]), "f"(c[2]), "f"(c[3]));
}
__device__ __forceinline__ void mma_p(int p, float (&d)[4], uint32_t a0, uint32_t a1, uint32_t a2, uint32_t a3, uint32_t b0, uint32_t b1) {
  asm volatile("{\n.reg .pred q;\nsetp.ne.b32 q, %10, 0;\n"
               "@q mma.sync.aligned.m16n8k16.row.col.f32.bf16.bf16.f32 {%0,%1,%2,%3},{%4,%5,%6,%7},{%8,%9},{%0,%1,%2,%3};\n}\n"
               : "+f"(d[0]), "+f"(d[1]), "+f"(d[2]), "+f"(d[3])
               : "r"(a0), "r"(a1), "r"(a2), "r"(a3), "r"(b0), "r"(b1), "r"(p));
}
__device__ __forceinline__ void mmac_p(int p, float (&d)[4], uint32_t a0, uint32_t a1, uint32_t a2, uint32_t a3, uint32_t b0,
                                       uint32_t b1, const float (&c)[4]) {
  asm volatile("{\n.reg .pred q;\nsetp.ne.b32 q, %14, 0;\n"
               "@q mma.sync.aligned.m16n8k16.row.col.f32.bf16.bf16.f32 {%0,%1,%2,%3},{%4,%5,%6,%7},{%8,%9},{%10,%11,%12,%13};\n}\n"
               : "+f"(d[0]), "+f"(d[1]), "+f"(d[2]), "+f"(d[3])
               : "r"(a0), "r"(a1), "r"(a2), "r"(a3), "r"(b0), "r"(b1), "f"(c[0]), "f"(c[1]), "f"(c[2]), "f"(c[3]), "r"(p));
}
__device__ __forceinline__ void mma_k8(float (&d)[4], uint32_t a0, uint32_t a1, uint32_t b0) {
  asm volatile("mma.sync.aligned.m16n8k8.row.col.f32.bf16.bf16.f32 {%0,%1,%2,%3},{%4,%5},{%6},{%0,%1,%2,%3};"
               : "+f"(d[0]), "+f"(d[1]), "+f"(d[2]), "+f"(d[3]) : "r"(a0), "r"(a1), "r"(b0));
}
__device__ __forceinline__ void mma0(float& d0, float& d1, float& d2, float& d3, uint32_t a0, uint32_t a1, uint32_t a2,
                                     uint32_t a3, uint32_t b0, uint32_t b1) {
  asm volatile("mma.sync.aligned.m16n8k16.row.col.f32.bf16.bf16.f32 {%0,%1,%2,%3},{%4,%5,%6,%7},{%8,%9},{%10,%10,%10,%10};"
               : "=f"(d0), "=f"(d1), "=f"(d2), "=f"(d3)
               : "r"(a0), "r"(a1), "r"(a2), "r"(a3), "r"(b0), "r"(b1), "f"(0.f));
}
__device__ __forceinline__ uint32_t pack_bf(float lo, float hi) {
  uint32_t r;
  asm("cvt.rn.bf16x2.f32 %0, %1, %2;" : "=r"(r) : "f"(hi), "f"(lo));
  return r;
}
__device__ __forceinline__ float bf_lo(uint32_t w) { return __uint_as_float(w << 16); }
__device__ __forceinline__ float bf_hi(uint32_t w) { return __uint_as_float(w & 0xffff0000u); }
__device__ __forceinline__ float bf_round(float x) { return __bfloat162float(__float2bfloat16_rn(x)); }
__device__ __forceinline__ uint32_t bmax2(uint32_t a, uint32_t b) {
  uint32_t r; asm("max.bf16x2 %0, %1, %2;" : "=r"(r) : "r"(a), "r"(b)); return r;
}
__device__ __forceinline__ uint32_t bmin2(uint32_t a, uint32_t b) {
  uint32_t r; asm("min.bf16x2 %0, %1, %2;" : "=r"(r) : "r"(a), "r"(b)); return r;
}
__device__ __forceinline__ float ex2(float x) { float r; asm("ex2.approx.ftz.f32 %0, %1;" : "=f"(r) : "f"(x)); return r; }
__device__ __forceinline__ float rcp(float x) { float r; asm("rcp.approx.ftz.f32 %0, %1;" : "=f"(r) : "f"(x)); return r; }
__device__ __forceinline__ void ldsm4(uint32_t (&r)[4], uint32_t a) {
  asm volatile("ldmatrix.sync.aligned.m8n8.x4.shared.b16 {%0,%1,%2,%3}, [%4];"
               : "=r"(r[0]), "=r"(r[1]), "=r"(r[2]), "=r"(r[3]) : "r"(a) : "memory");
}
__device__ __forceinline__ void ldsm4t(uint32_t (&r)[4], uint32_t a) {
  asm volatile("ldmatrix.sync.aligned.m8n8.x4.trans.shared.b16 {%0,%1,%2,%3}, [%4];"
               : "=r"(r[0]), "=r"(r[1]), "=r"(r[2]), "=r"(r[3]) : "r"(a) : "memory");
}
__device__ __forceinline__ void stsm4(uint32_t a, uint32_t r0, uint32_t r1, uint32_t r2, uint32_t r3) {
  asm volatile("stmatrix.sync.aligned.m8n8.x4.shared.b16 [%0], {%1,%2,%3,%4};"
               ::"r"(a), "r"(r0), "r"(r1), "r"(r2), "r"(r3) : "memory");
}
__device__ __forceinline__ uint32_t lds32(uint32_t a) {
  uint32_t r; asm volatile("ld.shared.u32 %0, [%1];" : "=r"(r) : "r"(a) : "memory"); return r;
}
__device__ __forceinline__ uint32_t lds16(uint32_t a) {
  uint32_t r; asm volatile("{\n.reg .u16 h;\nld.shared.u16 h, [%1];\ncvt.u32.u16 %0, h;\n}\n" : "=r"(r) : "r"(a) : "memory"); return r;
}
__device__ __forceinline__ uint2 lds64(uint32_t a) {
  uint2 r; asm volatile("ld.shared.v2.u32 {%0,%1}, [%2];" : "=r"(r.x), "=r"(r.y) : "r"(a) : "memory"); return r;
}
__device__ __forceinline__ uint4 lds128(uint32_t a) {
  uint4 r;
  asm volatile("ld.shared.v4.u32 {%0,%1,%2,%3}, [%4];" : "=r"(r.x), "=r"(r.y), "=r"(r.z), "=r"(r.w) : "r"(a) : "memory");
  return r;
}
__device__ __forceinline__ void sts32(uint32_t a, uint32_t v) { asm volatile("st.shared.u32 [%0], %1;" ::"r"(a), "r"(v) : "memory"); }
__device__ __forceinline__ void sts16(uint32_t a, uint32_t v) {
  asm volatile("{\n.reg .u16 h;\ncvt.u16.u32 h, %1;\nst.shared.u16 [%0], h;\n}\n" ::"r"(a), "r"(v) : "memory");
}
__device__ __forceinline__ void sts64(uint32_t a, uint32_t x, uint32_t y) {
  asm volatile("st.shared.v2.u32 [%0], {%1,%2};" ::"r"(a), "r"(x), "r"(y) : "memory");
}
__device__ __forceinline__ void sts128(uint32_t a, uint32_t x, uint32_t y, uint32_t z, uint32_t w) {
  asm volatile("st.shared.v4.u32 [%0], {%1,%2,%3,%4};" ::"r"(a), "r"(x), "r"(y), "r"(z), "r"(w) : "memory");
}
__device__ __forceinline__ uint4 ld_x(const uint4* p) {
  uint4 r;
  asm volatile("{\n.reg .b128 t;\nld.relaxed.gpu.global.b128 t, [%4];\nmov.b128 {%0,%1,%2,%3}, t;\n}\n"
               : "=r"(r.x), "=r"(r.y), "=r"(r.z), "=r"(r.w) : "l"(p) : "memory");
  return r;
}
__device__ __forceinline__ uint32_t ld_x32(const uint32_t* p) {
  uint32_t r; asm volatile("ld.relaxed.gpu.global.u32 %0, [%1];" : "=r"(r) : "l"(p) : "memory"); return r;
}
__device__ __forceinline__ void st_x(uint4* p, uint32_t x, uint32_t y, uint32_t z, uint32_t w) {
  asm volatile("{\n.reg .b128 t;\nmov.b128 t, {%1,%2,%3,%4};\nst.relaxed.gpu.global.b128 [%0], t;\n}\n"
               ::"l"(p), "r"(x), "r"(y), "r"(z), "r"(w) : "memory");
}
__device__ __forceinline__ void st_x_p(int p, uint4* a, uint32_t x, uint32_t y, uint32_t z, uint32_t w) {
  asm volatile("{\n.reg .b128 t;\n.reg .pred q;\nsetp.ne.b32 q, %5, 0;\nmov.b128 t, {%1,%2,%3,%4};\n@q st.relaxed.gpu.global.b128 [%0], t;\n}\n"
               ::"l"(a), "r"(x), "r"(y), "r"(z), "r"(w), "r"(p) : "memory");
}
__device__ __forceinline__ void sts64_p(int p, uint32_t a, uint32_t x, uint32_t y) {
  asm volatile("{\n.reg .pred q;\nsetp.ne.b32 q, %3, 0;\n@q st.shared.v2.u32 [%0], {%1,%2};\n}\n" ::"r"(a), "r"(x), "r"(y), "r"(p) : "memory");
}
__device__ __forceinline__ void st_x32(uint32_t* p, uint32_t x) {
  asm volatile("st.relaxed.gpu.global.u32 [%0], %1;" ::"l"(p), "r"(x) : "memory");
}
__device__ __forceinline__ uint32_t nz(uint32_t w) { return max(w, 1u); }
__device__ __forceinline__ uint32_t fu(float x) { return __float_as_uint(x); }
__device__ __forceinline__ float uf(uint32_t x) { return __uint_as_float(x); }

__device__ __forceinline__ void wgmma_ss_n96(float (&d)[48], uint64_t da, uint64_t db, int sc) {
  asm volatile("{\n.reg .pred p;\nsetp.ne.b32 p, %50, 0;\n"
      "wgmma.mma_async.sync.aligned.m64n96k16.f32.bf16.bf16 "
      "{%0,%1,%2,%3,%4,%5,%6,%7,%8,%9,%10,%11,%12,%13,%14,%15,%16,%17,%18,%19,%20,%21,%22,%23,%24,%25,%26,%27,%28,%29,%30,%31,%32,%33,%34,%35,%36,%37,%38,%39,%40,%41,%42,%43,%44,%45,%46,%47}, "
      "%48, %49, p, 1, 1, 0, 1;\n}\n"
      : "+f"(d[0]), "+f"(d[1]), "+f"(d[2]), "+f"(d[3]), "+f"(d[4]), "+f"(d[5]), "+f"(d[6]), "+f"(d[7]),
        "+f"(d[8]), "+f"(d[9]), "+f"(d[10]), "+f"(d[11]), "+f"(d[12]), "+f"(d[13]), "+f"(d[14]), "+f"(d[15]),
        "+f"(d[16]), "+f"(d[17]), "+f"(d[18]), "+f"(d[19]), "+f"(d[20]), "+f"(d[21]), "+f"(d[22]), "+f"(d[23]),
        "+f"(d[24]), "+f"(d[25]), "+f"(d[26]), "+f"(d[27]), "+f"(d[28]), "+f"(d[29]), "+f"(d[30]), "+f"(d[31]),
        "+f"(d[32]), "+f"(d[33]), "+f"(d[34]), "+f"(d[35]), "+f"(d[36]), "+f"(d[37]), "+f"(d[38]), "+f"(d[39]),
        "+f"(d[40]), "+f"(d[41]), "+f"(d[42]), "+f"(d[43]), "+f"(d[44]), "+f"(d[45]), "+f"(d[46]), "+f"(d[47])
      : "l"(da), "l"(db), "r"(sc));
}

__device__ __forceinline__ void wgmma_rs_n128(float (&d)[64], const uint4& a, uint64_t db, int sc) {
  asm volatile("{\n.reg .pred p;\nsetp.ne.b32 p, %69, 0;\n"
      "wgmma.mma_async.sync.aligned.m64n128k16.f32.bf16.bf16 "
      "{%0,%1,%2,%3,%4,%5,%6,%7,%8,%9,%10,%11,%12,%13,%14,%15,%16,%17,%18,%19,%20,%21,%22,%23,%24,%25,%26,%27,%28,%29,%30,%31,%32,%33,%34,%35,%36,%37,%38,%39,%40,%41,%42,%43,%44,%45,%46,%47,%48,%49,%50,%51,%52,%53,%54,%55,%56,%57,%58,%59,%60,%61,%62,%63}, "
      "{%64,%65,%66,%67}, %68, p, 1, 1, 1;\n}\n"
      : "+f"(d[0]), "+f"(d[1]), "+f"(d[2]), "+f"(d[3]), "+f"(d[4]), "+f"(d[5]), "+f"(d[6]), "+f"(d[7]),
        "+f"(d[8]), "+f"(d[9]), "+f"(d[10]), "+f"(d[11]), "+f"(d[12]), "+f"(d[13]), "+f"(d[14]), "+f"(d[15]),
        "+f"(d[16]), "+f"(d[17]), "+f"(d[18]), "+f"(d[19]), "+f"(d[20]), "+f"(d[21]), "+f"(d[22]), "+f"(d[23]),
        "+f"(d[24]), "+f"(d[25]), "+f"(d[26]), "+f"(d[27]), "+f"(d[28]), "+f"(d[29]), "+f"(d[30]), "+f"(d[31]),
        "+f"(d[32]), "+f"(d[33]), "+f"(d[34]), "+f"(d[35]), "+f"(d[36]), "+f"(d[37]), "+f"(d[38]), "+f"(d[39]),
        "+f"(d[40]), "+f"(d[41]), "+f"(d[42]), "+f"(d[43]), "+f"(d[44]), "+f"(d[45]), "+f"(d[46]), "+f"(d[47]),
        "+f"(d[48]), "+f"(d[49]), "+f"(d[50]), "+f"(d[51]), "+f"(d[52]), "+f"(d[53]), "+f"(d[54]), "+f"(d[55]),
        "+f"(d[56]), "+f"(d[57]), "+f"(d[58]), "+f"(d[59]), "+f"(d[60]), "+f"(d[61]), "+f"(d[62]), "+f"(d[63])
      : "r"(a.x), "r"(a.y), "r"(a.z), "r"(a.w), "l"(db), "r"(sc));
}

struct Params {
  const __nv_bfloat16 *x, *wphi, *wo, *u, *logA, *Aim, *Cre, *Cim, *logdt, *Dskip;
  __nv_bfloat16* out;
};

__device__ __forceinline__ uint4 tr_row(const uint4 (&v)[8], int i) {
  uint32_t o[4];
#pragma unroll
  for (int m = 0; m < 4; m++) {
    const uint4 &ra = v[2 * m], &rb = v[2 * m + 1];
    const int k = i >> 1;
    const uint32_t xa = k == 0 ? ra.x : k == 1 ? ra.y : k == 2 ? ra.z : ra.w;
    const uint32_t xb = k == 0 ? rb.x : k == 1 ? rb.y : k == 2 ? rb.z : rb.w;
    o[m] = __byte_perm(xa, xb, (i & 1) ? 0x7632 : 0x5410);
  }
  return make_uint4(o[0], o[1], o[2], o[3]);
}

struct cpx { float r, i; };
__device__ __forceinline__ cpx cmul(cpx a, cpx b) { return {a.r * b.r - a.i * b.i, a.r * b.i + a.i * b.r}; }
__device__ __forceinline__ cpx csq(cpx a) { return {a.r * a.r - a.i * a.i, 2.f * (a.r * a.i)}; }
__device__ __forceinline__ cpx polar(float e, float t) {
  const float m = ex2(e);
  return {m * __cosf(t), m * __sinf(t)};
}

struct KgenRaw { unsigned short la, ai, cr, ci, ldt; };
__device__ __forceinline__ KgenRaw kgen_load(const Params& P, int d, int unit, int lane) {
  const int o = d * 128 + unit * 32 + lane;
  return {__ldg((const unsigned short*)P.logA + o), __ldg((const unsigned short*)P.Aim + o), __ldg((const unsigned short*)P.Cre + o),
          __ldg((const unsigned short*)P.Cim + o), __ldg((const unsigned short*)P.logdt + d)};
}
__device__ __forceinline__ void kgen_unit(const KgenRaw& r, int lane, uint32_t buf, uint32_t open_bar, float& dt,
                                          float (&k)[5][4], float& k2048) {
  dt = bf_round(expf(bf_lo(r.ldt)));
  const float a2 = -(bf_round(expf(bf_lo(r.la))) * dt) * 1.4426950408889634f;
  const float f = bf_lo(r.ai) * dt;
  const float r128 = f * 20.371832715762604f;
  const cpx C = {bf_lo(r.cr), -bf_lo(r.ci)};
  const uint32_t sa = buf + (lane & 7) * 128 + ((((lane >> 3) ^ lane) & 7) << 4);
  const uint32_t lb = buf + (lane >> 3) * 128 + (((lane ^ (lane >> 3)) & 7) << 4);
  const uint32_t la = buf + ((lane >> 3) & 1) * 1024 + (lane >> 4) * 128 + (((lane ^ (lane >> 4)) & 7) << 4);
  auto put = [&](const cpx (&v)[8], uint32_t off) {
    stsm4(sa + off, pack_bf(v[0].r, v[0].i), pack_bf(v[1].r, v[1].i), pack_bf(v[2].r, v[2].i), pack_bf(v[3].r, v[3].i));
    stsm4((sa ^ 64) + off, pack_bf(v[4].r, v[4].i), pack_bf(v[5].r, v[5].i), pack_bf(v[6].r, v[6].i), pack_bf(v[7].r, v[7].i));
  };
  uint32_t A[4][4], B[5][2][4];
  auto getB = [&](int j, uint32_t off) {
    __syncwarp();
    ldsm4(B[j][0], lb + off);
    ldsm4(B[j][1], (lb ^ 64) + 512 + off);
  };
  cpx t0[8], t1[8], t2[8], t3[8], t4[8];
  t0[0] = {1.f, 0.f};
  t0[1] = polar(a2, f);
  t1[0] = polar(a2 * 128.f, (r128 - rintf(r128)) * 6.283185307179586f);
  t0[2] = csq(t0[1]); t0[4] = csq(t0[2]);
  t2[0] = csq(t1[0]); t3[0] = csq(t2[0]); t4[0] = csq(t3[0]);
  t0[3] = cmul(t0[2], t0[1]); t0[5] = cmul(t0[4], t0[1]); t0[6] = cmul(t0[4], t0[2]); t0[7] = cmul(t0[4], t0[3]);
  put(t0, 2048); getB(0, 2048);
  {
    cpx w8 = csq(t0[4]);
    w8.i = -w8.i;
    const cpx w16 = csq(w8), w32 = csq(w16), w64 = csq(w32);
    cpx a[8];
    a[0] = C; a[1] = cmul(C, w8);
    a[2] = cmul(a[0], w16); a[3] = cmul(a[1], w16);
#pragma unroll
    for (int i = 0; i < 4; i++) a[4 + i] = cmul(a[i], w32);
    put(a, 0);
#pragma unroll
    for (int i = 0; i < 8; i++) a[i] = cmul(a[i], w64);
    put(a, 1024);
    __syncwarp();
#pragma unroll
    for (int s = 0; s < 4; s++) ldsm4(A[s], (la ^ (s << 5)) + s * 256);
  }
#pragma unroll
  for (int i = 1; i < 8; i++) t1[i] = cmul(t0[i], t1[0]);
  put(t1, 2048); getB(1, 2048);
#pragma unroll
  for (int i = 1; i < 8; i++) t2[i] = cmul((i & 1) ? t1[i & 6] : t0[i & 6], t2[0]);
  put(t2, 0); getB(2, 0);
#pragma unroll
  for (int i = 1; i < 8; i++) t3[i] = cmul((i & 2) ? t2[i & 5] : ((i & 1) ? t1[i & 4] : t0[i & 4]), t3[0]);
  put(t3, 1024); getB(3, 1024);
#pragma unroll
  for (int i = 1; i < 8; i++) t4[i] = cmul((i & 4) ? t3[i & 3] : ((i & 2) ? t2[i & 1] : t1[0]), t4[0]);
  put(t4, 2048); getB(4, 2048);
  const cpx we = csq(t4[0]);
  k2048 += C.r * we.r + C.i * we.i;
  if (open_bar) mbar_wait(open_bar);
#pragma unroll
  for (int s = 0; s < 4; s++)
#pragma unroll
    for (int j = 0; j < 5; j++)
      mma(k[j][0], k[j][1], k[j][2], k[j][3], A[s][0], A[s][1], A[s][2], A[s][3], B[j][s >> 1][2 * (s & 1)], B[j][s >> 1][2 * (s & 1) + 1]);
}

__device__ __forceinline__ void build_tables(uint32_t tb, int lane, float (&k)[5][4], float k2048) {
  const int g = lane >> 2, c = lane & 3;
  const uint32_t kc = tb + T_KC + 16;
  {
    const uint32_t a0 = kc + 16 * g + 4 * c, a2 = kc + 2 * (256 + 4 * g + c);
    const uint32_t a3 = kc + 2 * (384 + 2 * g + 64 * (c & 1) + (c >> 1)), a4 = kc + 2 * (512 + g + 32 * c);
#pragma unroll
    for (int r = 0; r < 2; r++) {
      sts32(a0 + 128 * r, pack_bf(k[0][2 * r], k[0][2 * r + 1]));
      sts32(a0 + 128 * r + 256, pack_bf(k[1][2 * r], k[1][2 * r + 1]));
      const uint32_t w2 = pack_bf(k[2][2 * r], k[2][2 * r + 1]);
      const uint32_t w3 = pack_bf(k[3][2 * r], k[3][2 * r + 1]);
      const uint32_t w4 = pack_bf(k[4][2 * r], k[4][2 * r + 1]);
      sts16(a2 + 64 * r, w2); sts16(a2 + 64 * r + 128, w2 >> 16);
      sts16(a3 + 32 * r, w3); sts16(a3 + 32 * r + 64, w3 >> 16);
      sts16(a4 + 16 * r, w4); sts16(a4 + 16 * r + 32, w4 >> 16);
    }
  }
  if (lane == 0) { sts16(kc + 2 * 640, pack_bf(k2048, 0.f)); sts16(kc - 2, 0); }
  __syncwarp();
  const uint32_t td = tb + T_D + 32;
  {
    const uint4 v = lds128(kc + 16 * lane);
    const uint32_t pv = lds16(kc + 16 * lane - 2);
    sts128(td + 32 * lane, __byte_perm(v.x, pv, 0x5410), __byte_perm(v.x, v.x, 0x1032), __byte_perm(v.y, v.x, 0x7610),
           __byte_perm(v.y, v.y, 0x1032));
    sts128(td + 32 * lane + 16, __byte_perm(v.z, v.y, 0x7610), __byte_perm(v.z, v.z, 0x1032),
           __byte_perm(v.w, v.z, 0x7610), __byte_perm(v.w, v.w, 0x1032));
  }
  {
    const uint2 v = lds64(kc + 512 + 8 * lane);
    const uint32_t k4 = lds16(kc + 512 + 8 * lane + 8);
    const uint32_t pv = lds16(kc + (lane == 0 ? 510 : 512 + 8 * lane));
    const uint32_t k22 = __byte_perm(v.y, v.y, 0x1010);
    sts128(td + 1024 + 32 * lane, __byte_perm(v.x, pv, 0x5410), __byte_perm(v.x, v.x, 0x1010),
           __byte_perm(v.x, v.x, 0x1032), __byte_perm(v.y, v.x, 0x7610));
    sts128(td + 1024 + 32 * lane + 16, k22, k22, __byte_perm(v.y, v.y, 0x1032), __byte_perm(k4, v.y, 0x7610));
  }
  {
    const uint32_t kk = lds16(kc + 2 * 384);
    const uint32_t w = lane < 3 ? (kk | (kk << 16)) : (lane == 3 ? (kk << 16) : 0u);
    if (lane < 24) sts32(td + 4 * (lane < 16 ? 512 + lane : lane - 24), w);
    const uint32_t lo_ = lds16(kc + 2 * 511), le_ = lds16(kc + 2 * 512);
    const uint32_t ja = tb + T_5 + (lane < 16 ? 4 * lane : 256 + 4 * lane);
    sts32(ja, lane == 16 ? (le_ << 16) : 0u);
    sts32(ja + 384, lane == 16 ? (lo_ << 16) : 0u);
    sts32(tb + (lane < 16 ? T_7 : T_9 - 64) + 4 * lane, 0u);
  }
#pragma unroll
  for (int s = 0; s < 2; s++) {
    const uint32_t b = kc + 2 * (s ? 512 : 384) + 8 * lane;
    const uint2 v = lds64(b);
    uint32_t em = lds16(b - 2), e0 = v.x;
    const uint32_t e4 = lds16(b + 8);
    if (lane == 0) { em = 0; e0 = 0; }
    sts64(tb + (s ? T_7 : T_3) + 64 + 8 * lane, __byte_perm(v.x, em, 0x5432), __byte_perm(v.y, v.x, 0x7632));
    sts64(tb + (s ? T_9 : T_5) + 64 + 8 * lane, __byte_perm(v.y, e0, 0x5410), __byte_perm(e4, v.y, 0x5410));
  }
  __syncwarp();
}

__device__ __forceinline__ uint32_t box2w(int lo, int n, int o) {
  return ((unsigned)(o - lo) < (unsigned)n ? 0x3F80u : 0u) | ((unsigned)(o + 1 - lo) < (unsigned)n ? 0x3F800000u : 0u);
}

__device__ __forceinline__ void conv_channel(uint32_t ub, uint32_t tb, int lane, uint4* ydst) {
  const int g = lane >> 2, c = lane & 3, x = g - 2 * c;
  const uint32_t st = tb + T_ST + lane * 8;
  const int mi = lane >> 3;
  const uint32_t qa = ub + U_PAD + 16 * (lane & 7) + ((mi == 0 || mi == 3) ? U_ODD : 0) - (mi == 0 ? 16 : 0);
  const uint32_t kv = lds16(tb + T_KC + 16 + 2 * 512);
  {
    const uint32_t hb = ub + U_PAD + (mi & 1) * U_ODD + 16 * ((lane >> 4) + (lane & 7)) - 16;
    const int oh = c < 2 ? 8 + 2 * c : 2 * c - 8;
    const uint32_t bx0 = box2w(g - 4, 9, 2 * c), bx1 = box2w(g - 3, 7, 2 * c), bx2 = box2w(g - 4, 9, oh), bx3 = box2w(g - 3, 7, oh);
    uint32_t f7[9], f9a[9], f9b[9];
    const uint32_t fa = tb + T_7 + 4 * (8 + x);
#pragma unroll
    for (int m = 0; m < 9; m++) {
      f7[m] = lds32(fa + 32 * m);
      f9b[m] = lds32(fa + 320 + 32 * m);
      f9a[m] = lds32(fa + 316 + 32 * m);
    }
    mbar_wait(BAR(MB_EMPTY + 15));
    TS(36);
    uint32_t z09[8], z07[8], zm9[8], zm7[8];
#pragma unroll
    for (int i = 0; i < 8; i++) {
      uint32_t h[4];
      ldsm4(h, hb + 128 * i);
      float y0, y1, y2, y3, w0, w1, w2, w3;
      mma0(y0, y1, y2, y3, bx0, bx1, bx2, bx3, h[2], c < 2 ? h[3] : h[1]);
      mma0(w0, w1, w2, w3, bx0, bx1, bx2, bx3, h[1], c < 2 ? h[2] : h[0]);
      z09[i] = pack_bf(y0, y1); z07[i] = pack_bf(y2, y3);
      zm9[i] = pack_bf(w0, w1); zm7[i] = pack_bf(w2, w3);
    }
    float a[4][2][4];
#pragma unroll
    for (int kap = 0; kap < 4; kap++)
#pragma unroll
      for (int sg = 0; sg < 2; sg++)
#pragma unroll
        for (int bk = 3; bk >= kap; bk--) {
          const int m = 2 * (bk - kap) + 1;
          float(&a0)[4] = a[bk][0];
          float(&a1)[4] = a[bk][1];
          if (sg == 0 && kap == 0) {
            mma0(a0[0], a0[1], a0[2], a0[3], f9a[m], f9a[m + 1], f9a[m - 1], f9a[m], z09[0], z09[1]);
            mma0(a1[0], a1[1], a1[2], a1[3], f9b[m], f9b[m + 1], f9b[m - 1], f9b[m], zm9[0], zm9[1]);
          } else if (sg == 0) {
            mma(a0[0], a0[1], a0[2], a0[3], f9a[m], f9a[m + 1], f9a[m - 1], f9a[m], z09[2 * kap], z09[2 * kap + 1]);
            mma(a1[0], a1[1], a1[2], a1[3], f9b[m], f9b[m + 1], f9b[m - 1], f9b[m], zm9[2 * kap], zm9[2 * kap + 1]);
          } else {
            mma(a0[0], a0[1], a0[2], a0[3], f7[m], f7[m + 1], f7[m - 1], f7[m], zm7[2 * kap], zm7[2 * kap + 1]);
            mma(a1[0], a1[1], a1[2], a1[3], f7[m], f7[m + 1], f7[m - 1], f7[m], z07[2 * kap], z07[2 * kap + 1]);
          }
        }
#pragma unroll
    for (int bk = 0; bk < 4; bk++) {
      sts64(st + 256 * (8 + 2 * bk), pack_bf(a[bk][0][0], a[bk][0][1]), pack_bf(a[bk][1][0], a[bk][1][1]));
      sts64(st + 256 * (9 + 2 * bk), pack_bf(a[bk][0][2], a[bk][0][3]), pack_bf(a[bk][1][2], a[bk][1][3]));
    }
  }
  TS(44);
  {
    const int oh = c < 3 ? 2 * c : -10;
    const uint32_t bx0 = box2w(g - 10, 5, 2 * c - 8), bx1 = box2w(g - 5, 3, 2 * c - 8), bx2 = box2w(g - 10, 5, oh), bx3 = box2w(g - 5, 3, oh);
    const uint32_t lb0 = ((unsigned)(x + 5) < 2u ? kv : 0u) | ((unsigned)(x + 4) < 2u ? kv << 16 : 0u);
    const uint32_t lb1 = ((unsigned)(x - 3) < 2u ? kv : 0u) | ((unsigned)(x - 4) < 2u ? kv << 16 : 0u);
    const int q0 = g - 1, q1 = c < 3 ? g : g - 2;
    uint32_t y0a = ub + U_PAD + (q0 & 1) * U_ODD + 16 * (q0 >> 1) + 4 * c;
    uint32_t y1a = ub + U_PAD + (q1 & 1) * U_ODD + 16 * (q1 >> 1) + 4 * c;
    uint2 a5[10], a3[10];
    const uint32_t aa = tb + T_5 + 4 * (8 + 2 * g - 2 * c);
#pragma unroll
    for (int m = 0; m < 10; m++) { a5[m] = lds64(aa + 32 * m); a3[m] = lds64(aa + 384 + 32 * m); }
    float T[6][4];
#pragma unroll
    for (int i = 0; i < 6; i++) T[i][0] = T[i][1] = T[i][2] = T[i][3] = 0.f;
    uint32_t x5[2] = {0, 0}, x3[2] = {0, 0}, yb[4], lq[4];
    uint32_t lqa = qa, sta = st + 256 * 8;
    uint2 sv;
    auto fetch = [&]() {
      yb[0] = lds32(y0a); yb[1] = lds32(y1a); yb[2] = lds32(y0a + 64); yb[3] = lds32(y1a + 64);
      ldsm4(lq, lqa);
      sv = lds64(min(sta, st + 256 * 15));
      y0a += 128; y1a += 128; lqa += 128; sta += 256;
    };
    fetch();
#pragma unroll 2
    for (int kap = -1; kap < 13; kap++) {
      float yn[2][4];
      mma0(yn[0][0], yn[0][1], yn[0][2], yn[0][3], bx0, bx1, bx2, bx3, yb[0], yb[1]);
      mma0(yn[1][0], yn[1][1], yn[1][2], yn[1][3], bx0, bx1, bx2, bx3, yb[2], yb[3]);
      sts64_p(kap > 0, sta - 256 * 7, pack_bf(T[0][0], T[0][1]), pack_bf(T[0][2], T[0][3]));
#pragma unroll
      for (int i = 0; i < 5; i++)
        mmac_p((unsigned)kap < 12u - i, T[i], a5[2 * i + 1].x, a5[2 * i + 1].y, a5[2 * i].x, a5[2 * i].y, x5[0], x5[1], T[i + 1]);
      const float ci[4] = {bf_lo(sv.x), bf_hi(sv.x), bf_lo(sv.y), bf_hi(sv.y)};
      mmac_p(kap < 7, T[5], lq[0], lq[1], lq[2], lq[3], lb0, lb1, ci);
      fetch();
#pragma unroll
      for (int i = 0; i < 5; i++)
        mma_p((unsigned)kap < 12u - i, T[i], a3[2 * i + 1].x, a3[2 * i + 1].y, a3[2 * i].x, a3[2 * i].y, x3[0], x3[1]);
#pragma unroll
      for (int hh = 0; hh < 2; hh++) { x5[hh] = pack_bf(yn[hh][0], yn[hh][1]); x3[hh] = pack_bf(yn[hh][2], yn[hh][3]); }
    }
  }
  TS(45);
  {
    uint32_t F[66];
    const uint32_t fa = tb + T_D + 32 + 4 * x;
#pragma unroll
    for (int m = 0; m < 66; m++) F[m] = lds32(fa + 32 * m);
    float T[5][4];
#pragma unroll
    for (int i = 0; i < 5; i++) T[i][0] = T[i][1] = T[i][2] = T[i][3] = 0.f;
    uint32_t qd[8][4], held[2] = {0, 0};
    uint32_t qp = qa + 128 * 15, sta = st + 256 * 14;
    uint4* yd = ydst + 19 * 16;
#pragma unroll
    for (int i = 0; i < 6; i++) ldsm4(qd[i], qp - 16 * i);
    uint2 sv = lds64(sta + 256);
    float ci[4] = {bf_lo(sv.x), bf_hi(sv.x), bf_lo(sv.y), bf_hi(sv.y)};
    mbar_wait(BAR(MB_ZOK));
    TS(46);
#pragma unroll 2
    for (int be = 15; be >= 0; be--) {
#pragma unroll
      for (int k = 4; k >= 1; k--)
        mmac_p(be <= 15 - k, T[k], qd[0][0], qd[0][1], qd[0][2], qd[0][3], F[16 * k + 1], F[16 * k], T[k - 1]);
      mmac(T[0], qd[0][0], qd[0][1], qd[0][2], qd[0][3], F[1], F[0], ci);
      ldsm4(qd[6], qp - 16 * 6);
      ldsm4(qd[7], qp - 16 * 7);
      sv = lds64(sta);
#pragma unroll
      for (int i = 1; i < 8; i++) {
#pragma unroll
        for (int k = 3; k >= 0; k--)
          mma_p(k == 0 || be <= 15 - k, T[k], qd[i][0], qd[i][1], qd[i][2], qd[i][3], F[16 * k + 2 * i + 1], F[16 * k + 2 * i]);
        if (i < 7) ldsm4(qd[i - 1], qp - 128 - 16 * (i - 1));
        if (i == 2) {
          const uint32_t w0 = pack_bf(T[4][0], T[4][1]), w1 = pack_bf(T[4][2], T[4][3]);
          st_x_p(be <= 10 && !(be & 1), yd, nz(w0), w1, held[0], held[1]);
          held[0] = w0; held[1] = w1;
        }
        if (i == 4) {
          if (be <= 4) sv = make_uint2(0, 0);
          ci[0] = bf_lo(sv.x); ci[1] = bf_hi(sv.x); ci[2] = bf_lo(sv.y); ci[3] = bf_hi(sv.y);
        }
      }
      qp -= 128; sta -= 256; yd -= 16;
    }
#pragma unroll
    for (int B = 1; B >= 0; B--)
      st_x(ydst + B * 32, nz(pack_bf(T[2 * B][0], T[2 * B][1])), pack_bf(T[2 * B][2], T[2 * B][3]),
           pack_bf(T[2 * B + 1][0], T[2 * B + 1][1]), pack_bf(T[2 * B + 1][2], T[2 * B + 1][3]));
  }
}

__device__ __forceinline__ void feat(const float (&acc)[48], int j0, const uint32_t (&wf)[4], uint32_t* w) {
  const uint32_t a0 = pack_bf(acc[4 * j0], acc[4 * j0 + 1]), a1 = pack_bf(acc[4 * j0 + 2], acc[4 * j0 + 3]);
  const uint32_t a2 = pack_bf(acc[4 * j0 + 4], acc[4 * j0 + 5]), a3 = pack_bf(acc[4 * j0 + 6], acc[4 * j0 + 7]);
  float p[8];
  mma0(p[0], p[1], p[2], p[3], a0, a1, a2, a3, wf[0], wf[1]);
  mma0(p[4], p[5], p[6], p[7], a0, a1, a2, a3, wf[2], wf[3]);
  w[0] = pack_bf(p[0], p[2]); w[1] = pack_bf(p[1], p[3]); w[2] = pack_bf(p[4], p[6]); w[3] = pack_bf(p[5], p[7]);
}
__device__ __forceinline__ void dual_softmax(const uint32_t* w, uint32_t* e) {
  const float L = 1.44268798828125f;
  uint32_t mx = bmax2(bmax2(w[0], w[1]), bmax2(w[2], w[3]));
  uint32_t mn = bmin2(bmin2(w[0], w[1]), bmin2(w[2], w[3]));
  mx = bmax2(mx, __shfl_xor_sync(0xffffffffu, mx, 1));
  mn = bmin2(mn, __shfl_xor_sync(0xffffffffu, mn, 1));
  mx = bmax2(mx, __shfl_xor_sync(0xffffffffu, mx, 2));
  mn = bmin2(mn, __shfl_xor_sync(0xffffffffu, mn, 2));
  const float mx0 = bf_lo(mx) * -L, mx1 = bf_hi(mx) * -L, mn0 = bf_lo(mn) * L, mn1 = bf_hi(mn) * L;
  float ep[2][4], em[2][4];
#pragma unroll
  for (int i = 0; i < 4; i++) {
    const float x0 = bf_lo(w[i]), x1 = bf_hi(w[i]);
    ep[0][i] = ex2(fmaf(x0, L, mx0)); em[0][i] = ex2(fmaf(x0, -L, mn0));
    ep[1][i] = ex2(fmaf(x1, L, mx1)); em[1][i] = ex2(fmaf(x1, -L, mn1));
  }
  __half2 sp = __floats2half2_rn((ep[0][0] + ep[0][1]) + (ep[0][2] + ep[0][3]), (ep[1][0] + ep[1][1]) + (ep[1][2] + ep[1][3]));
  __half2 sm = __floats2half2_rn((em[0][0] + em[0][1]) + (em[0][2] + em[0][3]), (em[1][0] + em[1][1]) + (em[1][2] + em[1][3]));
  sp = __hadd2(sp, __shfl_xor_sync(0xffffffffu, sp, 1));
  sm = __hadd2(sm, __shfl_xor_sync(0xffffffffu, sm, 1));
  sp = __hadd2(sp, __shfl_xor_sync(0xffffffffu, sp, 2));
  sm = __hadd2(sm, __shfl_xor_sync(0xffffffffu, sm, 2));
  const float rp[2] = {rcp(__low2float(sp)), rcp(__high2float(sp))}, rm[2] = {rcp(__low2float(sm)), rcp(__high2float(sm))};
#pragma unroll
  for (int i = 0; i < 4; i++) {
    const int r = i & 1, k = i & 2;
    e[i] = pack_bf(ep[r][k] * rp[r], ep[r][k + 1] * rp[r]);
    e[4 + i] = pack_bf(em[r][k] * rm[r], em[r][k + 1] * rm[r]);
  }
}

__global__ void __launch_bounds__(NTHREADS, 1)
fused_kernel(const Params P, const __grid_constant__ CUtensorMap mx, const __grid_constant__ CUtensorMap mw,
             const __grid_constant__ CUtensorMap mo, const __grid_constant__ CUtensorMap mu,
             const __grid_constant__ CUtensorMap mout) {
  asm volatile("prefetch.tensormap [%0];" ::"l"(&mw) : "memory");
  asm volatile("prefetch.tensormap [%0];" ::"l"(&mx) : "memory");
  constexpr uint32_t sb = SB;
  const int tid = threadIdx.x, lane = tid & 31;
  const int warp = __shfl_sync(0xffffffffu, tid >> 5, 0);
  const int b = blockIdx.x, oct = b >> 3, i8 = b & 7;
  const int rt = oct < 8 ? oct : 15 - oct;
  const int hp = (oct >> 3) * 8 + i8;

  if (warp >= 12) asm volatile("setmaxnreg.dec.sync.aligned.u32 32;");
  if (warp == 12) {
    if (lane == 0) {
#pragma unroll
      for (int i = 0; i < 8; i++) mbar_init(BAR(MB_FULL + i), 1);
      asm volatile("fence.mbarrier_init.release.cluster;" ::: "memory");
    }
    __syncwarp();
    if (lane < 8) mbar_expect(BAR(MB_FULL) + 8 * lane, lane < 7 ? 28672 : 29696);
    __syncwarp();
    nb_arrive(NB_PREP, 448);
#pragma unroll 1
    for (int kb = 0; kb < 8; kb++) {
      e_tma3d(sb + OFF_W + kb * 12288, &mw, BAR(MB_FULL) + 8 * kb, hp * 32, kb * 64, 0);
      if (kb < 5) e_tma2d(sb + OFF_X + (kb < 2 ? kb + 3 : kb - 2) * 16384, &mx, BAR(MB_FULL) + 8 * kb, kb * 64, rt * 256);
    }
    e_prefetch(P.x + (size_t)(rt * 256 + hp * 8) * 512, 8192);
    e_bulk(sb + OFF_PHI, P.wphi + hp * 512, 1024, BAR(MB_FULL + 7));
    if (smem_u32(smem_raw) != SB) __trap();
  }
  if (warp >= 12) {
    if (warp == 12) {
      nb_sync(NB_PROD, 64);
      uint32_t slot = sb + OFF_X + 3 * 16384;
#pragma unroll 1
      for (int n = 0; n < 11; n++) {
        mbar_wait(BAR(MB_EMPTY) + 8 * n);
        const int m = n + 5;
        e_tma2d(slot, &mx, BAR(MB_FULL) + 8 * m, (m & 7) * 64, rt * 256 + (m >> 3) * 128);
        slot = slot == sb + OFF_X + 4 * 16384 ? sb + OFF_X : slot + 16384;
        if (n == STEP_PF) e_prefetch(P.x + (size_t)(rt * 256 + 128 + hp * 8) * 512, 8192);
        if (n == STEP_U) {
          mbar_wait(BAR(MB_KREAD));
          asm volatile("fence.proxy.async.shared::cta;" ::: "memory");
          e_tma5d(sb + OFF_STG0, &mu, BAR(MB_URAW), i8 * 64, oct * 4);
        }
        if (n == 7) e_prefetch(P.wo + (size_t)b * 2048, 4096);
      }
#pragma unroll 1
      for (int i = 0; i < 8; i++) {
        mbar_wait(BAR(MB_EMPTY + 10) + 8 * ((0x54332100u >> (4 * i)) & 7));
        const int w0 = (0x54736210u >> (4 * i)) & 7;
        const int col = (hp & 3) * 128 + (w0 >> 2) * 64;
        e_tma2d(sb + OFF_W + w0 * 16384, &mo, BAR(MB_WO) + 8 * (w0 >> 2), col, w0 * 64);
        e_tma2d(sb + OFF_W + w0 * 16384 + 8192, &mo, BAR(MB_WO) + 8 * (w0 >> 2), col ^ 64, w0 * 64);
      }
    } else {
      if (warp == 13) {
        if (lane == 0) {
#pragma unroll
          for (int i = 8; i < 40; i++) mbar_init(BAR(i), i < MB_EMPTY ? 1 : (i < MB_RAWDONE ? 4 : (i == MB_RAWDONE ? 3 : 8)));
          asm volatile("fence.mbarrier_init.release.cluster;" ::: "memory");
        }
        __syncwarp();
        if (lane < 11) mbar_expect(BAR(MB_FULL + 8) + 8 * lane, lane < 9 ? 16384 : 65536);
        __syncwarp();
        nb_arrive(NB_PROD, 64);
        nb_arrive(NB_PREP, 448);
      }
      nb_sync(NB_RDY, 96);
      const unsigned cnt0 = ld_x32(g_cnt + 256);
      mbar_wait(BAR(MB_URAW));
      if (tid == 416) TS1(48);
      uint4* dst = g_uT + (size_t)(i8 * 64 + (lane >> 2)) * 256 + (lane & 1) * 128 + oct * 8 + ((lane >> 1) & 1);
#pragma unroll 1
      for (int i = warp - 13; i < 32; i += 3) {
        uint32_t r[4];
        ldsm4t(r, sb + OFF_STG0 + (i >> 3) * 4096 + lane * 128 + (((i ^ lane) & 7) << 4));
        dst[(i & 7) * 2048 + (i >> 3) * 2] = make_uint4(r[0], r[1], r[2], r[3]);
      }
      if (lane == 0) mbar_arrive(BAR(MB_RAWDONE));
      nb_sync(NB_INIT, 96);
      if (warp > 13) {
        mbar_wait(BAR(MB_EMPTY + ZERO_STEP));
        uint4* po = g_o + (size_t)(rt * 4 * 32 + hp * 2) * 128;
        uint4* py = g_y + (size_t)b * 1024;
        uint4* pp = g_part + (size_t)(hp * 8 + rt) * 144;
#pragma unroll 1
        for (int i = tid - 448; i < ZERO_N; i += 64) {
          st_x(po + (i >> 8) * 4096 + (i & 255), 0, 0, 0, 0);
          st_x(py + i, 0, 0, 0, 0);
          if (i < 144) st_x(pp + i, 0, 0, 0, 0);
        }
        nb_sync(NB_ZERO, 64);
        if (warp == 15) return;
      }
      if (lane == 0) TS1(warp == 13 ? 49 : 55);
      if (lane == 0)
        asm volatile("red.release.gpu.global.add.u32 [%0], %1;" ::"l"(g_cnt + (warp == 13 ? i8 : 8) * 32), "r"(warp == 13 ? 8 : 1) : "memory");
      if (lane == 0) TS1(warp == 13 ? 50 : 56);
#pragma unroll 1
      for (int i = 0; i < SPIN_MAX; i++) {
        unsigned v;
        asm volatile("ld.acquire.gpu.global.u32 %0, [%1];" : "=r"(v) : "l"(g_cnt + (warp == 13 ? b >> 4 : 8) * 32) : "memory");
        if ((int)(v - ((cnt0 & ~(unsigned)(NCTA - 1)) + NCTA)) >= 0) break;
      }
      if (lane == 0) TS1(warp == 13 ? 51 : 57);
      if (warp == 14) {
        if (lane == 0) mbar_arrive(BAR(MB_ZOK));
      } else {
        mbar_wait(BAR(MB_EMPTY + 11));
        sts128(sb + OFF_U + (lane >> 4) * U_CH + ((lane >> 3) & 1) * U_ODD + (lane & 7) * 16, 0, 0, 0, 0);
        sts128(sb + OFF_U + (2 + (lane >> 4)) * U_CH + ((lane >> 3) & 1) * U_ODD + (lane & 7) * 16, 0, 0, 0, 0);
        asm volatile("fence.proxy.async.global;" ::: "memory");
        __syncwarp();
        e_expect(BAR(MB_UFULL), 16384);
#pragma unroll 1
        for (int i = 0; i < 8; i++)
          e_bulk(sb + OFF_U + (i >> 1) * U_CH + (i & 1) * U_ODD + U_PAD, g_uT + (size_t)(b * 8 + i) * 128, 2048, BAR(MB_UFULL));
      }
    }
    return;
  }

  asm volatile("setmaxnreg.inc.sync.aligned.u32 160;");
  const int wg = warp >> 2, w = warp & 3, t = tid & 127;
  const int g = lane >> 2, c = lane & 3;
  const uint32_t tb = sb + OFF_T + w * T_CH;
  const int d = b * 4 + w;
  {
    KgenRaw raw = kgen_load(P, d, wg, lane);
    const KgenRaw raw3 = kgen_load(P, d, 3, lane);
    const unsigned short dsk = __ldg((const unsigned short*)P.Dskip + d);
    float k[5][4], k2048 = 0.f, dt;
#pragma unroll
    for (int j = 0; j < 5; j++) k[j][0] = k[j][1] = k[j][2] = k[j][3] = 0.f;
    const uint32_t kp = sb + OFF_STG0 + (warp & 7) * 3072;
#pragma unroll 1
    for (int r = 0; r <= (wg >> 1); r++) {
      kgen_unit(raw, lane, wg == 2 ? tb + 2048 - (T_CH * w & 127) : kp, r ? BAR(MB_EMPTY + 7) : 0u, dt, k, k2048);
      raw = raw3;
      TS(40 + wg + r);
      if (r == 0) {
        if (wg != 2) {
#pragma unroll
          for (int j = 0; j < 5; j++) sts128(kp + j * 512 + lane * 16, fu(k[j][0]), fu(k[j][1]), fu(k[j][2]), fu(k[j][3]));
          sts32(kp + 2560 + lane * 4, fu(k2048));
        } else if ((fu(k[0][0]) & fu(k[1][0]) & fu(k[2][0]) & fu(k[3][0]) & fu(k[4][0])) == 0xffffffffu) {
          sts32(kp, 0);
        }
        nb_sync(NB_PREP, 448);
        if (wg == 2) {
#pragma unroll 1
          for (int q = 0; q < 2; q++) {
            const uint32_t src = sb + OFF_STG0 + (q * 4 + w) * 3072;
#pragma unroll
            for (int j = 0; j < 5; j++) {
              const uint4 v = lds128(src + j * 512 + lane * 16);
              k[j][0] += uf(v.x); k[j][1] += uf(v.y); k[j][2] += uf(v.z); k[j][3] += uf(v.w);
            }
            k2048 += uf(lds32(src + 2560 + lane * 4));
          }
          __syncwarp();
          if (lane == 0) mbar_arrive(BAR(MB_KREAD));
        }
      }
    }
    if (wg == 2) {
      if (lane == 0 && (fu(k[0][0]) & fu(k[1][0]) & fu(k[2][0]) & fu(k[3][0]) & fu(k[4][0])) != 0xffffffffu)
        mbar_arrive(BAR(MB_CLOSE));
      TS(34);
#pragma unroll
      for (int o2 = 16; o2; o2 >>= 1) k2048 += __shfl_xor_sync(0xffffffffu, k2048, o2);
      const float sc = 2.f * dt;
#pragma unroll
      for (int j = 0; j < 5; j++) { k[j][0] *= sc; k[j][1] *= sc; k[j][2] *= sc; k[j][3] *= sc; }
      k2048 *= sc;
      if (lane == 0) k[0][0] += bf_lo(dsk);
      build_tables(tb, lane, k, k2048);
      TS(35);
      mbar_wait(BAR(MB_UFULL));
      conv_channel(sb + OFF_U + w * U_CH, tb, lane, g_y + (size_t)d * 256 + lane);
      nb_arrive(NB_BDONE, 384);
      TS(37);
      const int lam = w * 8 + g;
      const uint4* src = g_y + (size_t)(oct * 32 + c * 8) * 256 + i8 * 32 + lam;
      uint4 v[8];
#pragma unroll 1
      for (int it = 0; it < SPIN_MAX; it++) {
        uint32_t m = 0xffffffffu;
#pragma unroll
        for (int i = 0; i < 8; i++) v[i] = ld_x(src + i * 256);
#pragma unroll
        for (int i = 0; i < 8; i++) m = min(m, v[i].x);
        if (__all_sync(0xffffffffu, m != 0)) break;
      }
      __nv_bfloat16* dst = P.out + (size_t)(i8 * 256 + (lam >> 2) * 16 + (lam & 3) * 2) * 1024 + 512 + oct * 32 + c * 8;
#pragma unroll
      for (int i = 0; i < 8; i++) *(uint4*)(dst + (size_t)((i >> 2) * 128 + ((i >> 1) & 1) * 8 + (i & 1)) * 1024) = tr_row(v, i);
      TS(38);
      GT(63);
      return;
    }
    if (wg == 1) mbar_wait(BAR(MB_CLOSE));
    TS(wg * 16 + 1);
  }

  float acc[2][48];
  {
    uint32_t fb = BAR(MB_FULL) + 64 * wg;
    uint32_t da = (uint32_t)mkdesc(sb + OFF_X, 16, 0, 0) + (wg ? 1024 : 3072), db = (uint32_t)mkdesc(sb + OFF_W, 4096, 0, 0);
    constexpr uint64_t ha = mkdesc(0, 0, 1024, 1), hb = mkdesc(0, 0, 512, 2);
#pragma unroll 1
    for (int kb = 0; kb < 8; kb++) {
      mbar_wait(fb);
      if (kb == 0) TS(wg * 16 + 2);
      WG_FENCE();
#pragma unroll
      for (int k = 0; k < 4; k++) {
        wgmma_ss_n96(acc[0], ha | (da + 2 * k), hb | (db + 64 * k), k ? 1 : kb);
        wgmma_ss_n96(acc[1], ha | (da + 2 * k + 512), hb | (db + 64 * k), k ? 1 : kb);
      }
      WG_COMMIT();
      WG_WAIT(1);
      if (kb > 0 && lane == 0) mbar_arrive(fb + 8 * (MB_EMPTY - MB_FULL - 1));
      fb += 8; db += 768;
      da = da == (uint32_t)mkdesc(sb + OFF_X + 65536, 16, 0, 0) ? da - 4096 : da + 1024;
    }
    WG_WAIT(0);
    if (lane == 0) mbar_arrive(fb + 8 * (MB_EMPTY - MB_FULL - 1));
    mbar_wait(fb + 8 * (MB_EMPTY - MB_FULL - 1));
  }
  uint32_t wf[2][4];
  ldsm4t(wf[0], sb + OFF_PHI + (lane & 15) * 32 + (lane >> 4) * 16);
  ldsm4t(wf[1], sb + OFF_PHI + 512 + (lane & 15) * 32 + (lane >> 4) * 16);
  TS(wg * 16 + 3);

  uint32_t pw[32], eq[32];
#pragma unroll
  for (int u = 0; u < 4; u++)
#pragma unroll
    for (int h = 0; h < 2; h++) feat(acc[u & 1], (u < 2 ? 4 : 0) + 2 * h, wf[h], pw + 8 * u + 4 * h);
  {
    uint32_t all = 0xffffffffu;
#pragma unroll
    for (int i = 0; i < 16; i++) all &= pw[2 * i];
    if (wg == 0 && lane == 0 && all != 0xffffffffu) mbar_arrive(BAR(MB_CLOSE));
  }
  mbar_wait(BAR(MB_RAWDONE));
  const uint32_t stg0 = sb + OFF_STG0, stg1 = sb + OFF_X + 32768;
  uint32_t sl = (wg ? stg1 : stg0) + w * 3072 + lane * 16;
#pragma unroll
  for (int mt = 0; mt < 2; mt++)
#pragma unroll
    for (int h = 0; h < 2; h++) {
      const float* a = acc[mt] + 32 + 8 * h;
      stsm4(sl + mt * 12288 + 2048 + h * 512, pack_bf(a[0], a[1]), pack_bf(a[2], a[3]), pack_bf(a[4], a[5]), pack_bf(a[6], a[7]));
    }
#pragma unroll 1
  for (int u = 0; u < 4; u++) {
#pragma unroll
    for (int i = 0; i < 16; i++) eq[i] = eq[16 + i];
    dual_softmax(pw, eq + 16);
    dual_softmax(pw + 4, eq + 24);
    if (u < 2) {
#pragma unroll
      for (int i = 0; i < 4; i++) stsm4(sl + i * 512, eq[16 + 4 * i], eq[17 + 4 * i], eq[18 + 4 * i], eq[19 + 4 * i]);
      if (wg) nb_arrive(NB_ST0 + u, 256);
      sl += 12288;
    }
#pragma unroll
    for (int i = 0; i < 24; i++) pw[i] = pw[i + 8];
  }
  TS(wg * 16 + 4);
  const uint32_t kvs = stg0;
  if (wg == 0) {
    nb_sync(NB_WG0, 128);
    mbar_wait(BAR(MB_ZOK));
    mbar_wait(BAR(MB_EMPTY + 15));
    float kv[12];
#pragma unroll
    for (int i = 0; i < 12; i++) kv[i] = 0.f;
    const int mi = lane >> 3;
    const uint32_t ao = w * 512 + (lane & 7) * 16 + ((mi & 1) * 2 + (mi >> 1)) * 128, bo = 2048 + (w >> 1) * 512 + lane * 16;
#pragma unroll 1
    for (int j = 0; j < 4; j++) {
      if (j >= 2) nb_sync(NB_ST0 + j - 2, 256);
      const uint32_t sg = (j >= 2 ? stg1 : stg0) + (j & 1) * 12288;
      uint32_t a[4][4], bb[4][4];
#pragma unroll
      for (int s = 0; s < 4; s++) { ldsm4t(a[s], sg + s * 3072 + ao); ldsm4t(bb[s], sg + s * 3072 + bo); }
#pragma unroll
      for (int s = 0; s < 4; s++) {
        mma(kv[0], kv[1], kv[2], kv[3], a[s][0], a[s][1], a[s][2], a[s][3], bb[s][0], bb[s][1]);
        mma(kv[4], kv[5], kv[6], kv[7], a[s][0], a[s][1], a[s][2], a[s][3], bb[s][2], bb[s][3]);
        mma(kv[8], kv[9], kv[10], kv[11], a[s][0], a[s][1], a[s][2], a[s][3], 0x3F803F80u, 0x3F803F80u);
      }
    }
    uint4* pp = g_part + (size_t)(hp * 8 + rt) * 144;
    st_x(pp + t, nz(pack_bf(kv[0], kv[1])), pack_bf(kv[2], kv[3]), pack_bf(kv[4], kv[5]), pack_bf(kv[6], kv[7]));
    if (c < 2) st_x32((uint32_t*)(pp + 128) + w * 16 + c * 8 + g, nz(fu(c ? kv[10] : kv[8])));
    TS(5);
    const uint4* ps = g_part + (size_t)hp * 8 * 144 + t;
    const uint32_t* zs = (const uint32_t*)(g_part + (size_t)(hp * 8 + (lane >> 4) * 4) * 144 + 128) + w * 16 + (lane & 15);
    uint4 v[8];
    uint32_t zv[4];
#pragma unroll 1
    for (int it = 0; it < SPIN_MAX; it++) {
#pragma unroll
      for (int i = 0; i < 8; i++) v[i] = ld_x(ps + i * 144);
#pragma unroll
      for (int i = 0; i < 4; i++) zv[i] = ld_x32(zs + i * 576);
      uint32_t m = min(min(zv[0], zv[1]), min(zv[2], zv[3]));
#pragma unroll
      for (int i = 0; i < 8; i++) m = min(m, v[i].x);
      if (__all_sync(0xffffffffu, m != 0)) break;
    }
    float s4[4][4];
#pragma unroll
    for (int i = 0; i < 4; i++) s4[i][0] = s4[i][1] = s4[i][2] = s4[i][3] = 0.f;
    const uint32_t eye = (g >> 1) == c ? ((g & 1) ? 0x3F800000u : 0x3F80u) : 0u;
#pragma unroll
    for (int r = 0; r < 8; r++) {
      mma_k8(s4[(r & 1) * 2], v[r].x, v[r].y, eye);
      mma_k8(s4[(r & 1) * 2 + 1], v[r].z, v[r].w, eye);
    }
    float s[8];
#pragma unroll
    for (int i = 0; i < 8; i++) s[i] = s4[i >> 2][i & 3] + s4[2 + (i >> 2)][i & 3];
    float zsum = (uf(zv[0]) + uf(zv[1])) + (uf(zv[2]) + uf(zv[3]));
    zsum += __shfl_xor_sync(0xffffffffu, zsum, 16);
    stsm4(kvs + w * 512 + lane * 16, pack_bf(s[0], s[1]), pack_bf(s[2], s[3]), pack_bf(s[4], s[5]), pack_bf(s[6], s[7]));
    if (lane < 16) sts16(kvs + 2048 + (w * 16 + lane) * 2, pack_bf(zsum, 0.f));
    TS(6);
  }
  nb_sync(NB_KV, 256);
  {
    uint32_t kb_[4][4], zb[8];
#pragma unroll
    for (int i = 0; i < 4; i++) ldsm4t(kb_[i], kvs + i * 512 + lane * 16);
#pragma unroll
    for (int i = 0; i < 8; i++) zb[i] = lds32(kvs + 2048 + i * 16 + c * 4);
    uint4* od = g_o + (size_t)((rt * 4 + wg * 2) * 32 + hp * 2) * 128 + t;
#pragma unroll 1
    for (int mt = 0; mt < 2; mt++) {
#pragma unroll
      for (int h = 0; h < 2; h++) {
        const uint32_t* e = eq + 8 * h;
        float n[8], dn[4];
        mma0(dn[0], dn[1], dn[2], dn[3], e[0], e[1], e[2], e[3], zb[4 * h], zb[4 * h + 1]);
        mma0(n[0], n[1], n[2], n[3], e[0], e[1], e[2], e[3], kb_[2 * h][0], kb_[2 * h][1]);
        mma0(n[4], n[5], n[6], n[7], e[0], e[1], e[2], e[3], kb_[2 * h][2], kb_[2 * h][3]);
        mma(dn[0], dn[1], dn[2], dn[3], e[4], e[5], e[6], e[7], zb[4 * h + 2], zb[4 * h + 3]);
        mma(n[0], n[1], n[2], n[3], e[4], e[5], e[6], e[7], kb_[2 * h + 1][0], kb_[2 * h + 1][1]);
        mma(n[4], n[5], n[6], n[7], e[4], e[5], e[6], e[7], kb_[2 * h + 1][2], kb_[2 * h + 1][3]);
        const float r0 = rcp(dn[0] + 1e-6f), r1 = rcp(dn[2] + 1e-6f);
        st_x(od + h * 128, nz(pack_bf(n[0] * r0, n[1] * r0)), pack_bf(n[2] * r1, n[3] * r1), pack_bf(n[4] * r0, n[5] * r0),
             pack_bf(n[6] * r1, n[7] * r1));
      }
#pragma unroll
      for (int i = 0; i < 16; i++) eq[i] = eq[16 + i];
      od += 4096;
    }
  }
  TS(wg * 16 + 7);
  const int rb = rt * 4 + (hp >> 2);
  const uint4* osrc = g_o + (size_t)(rb * 32 + wg * 16) * 128 + t;
  uint4 af[16];
  {
    const uint32_t* probe = (const uint32_t*)(osrc - lane + (lane & 15) * 128 + (lane >> 4) * 31);
#pragma unroll 1
    for (int it = 0; it < SPIN_MAX; it++) {
      uint32_t m = ld_x32(probe);
#pragma unroll
      for (int i = 0; i < 4; i++) af[i] = ld_x(osrc + i * 128);
#pragma unroll
      for (int i = 0; i < 4; i++) m = min(m, af[i].x);
      if (__all_sync(0xffffffffu, m != 0)) break;
    }
  }
#pragma unroll
  for (int i = 4; i < 16; i++) af[i] = ld_x(osrc + i * 128);
  TS(wg * 16 + 8);
  mbar_wait(BAR(MB_WO) + 8 * wg);
  nb_sync(NB_BDONE, 384);
  TS(wg * 16 + 9);
  float oc[64];
  {
    const uint64_t db = mkdesc(sb + OFF_W, 8192, 1024, 1) + wg * 4096;
#pragma unroll
    for (int j = 0; j < 4; j++) {
      if (j) {
#pragma unroll 1
        for (int it = 0; it < SPIN_MAX; it++) {
          const uint32_t m = min(min(af[4 * j].x, af[4 * j + 1].x), min(af[4 * j + 2].x, af[4 * j + 3].x));
          if (__all_sync(0xffffffffu, m != 0)) break;
#pragma unroll
          for (int i = 0; i < 4; i++) af[4 * j + i] = ld_x(osrc + (4 * j + i) * 128);
        }
      }
      WG_FENCE();
#pragma unroll
      for (int k = 0; k < 4; k++) wgmma_rs_n128(oc, af[4 * j + k], db + 128 * k + 1024 * j, j | k);
    }
    WG_COMMIT();
    WG_WAIT(0);
  }
  TS(wg * 16 + 10);
  const uint32_t xo = stg1 + wg * 16384 + t * 16, xi = stg1 + (wg ^ 1) * 16384 + t * 16;
#pragma unroll
  for (int i = 0; i < 8; i++) sts128(xo + i * 2048, fu(oc[32 + 4 * i]), fu(oc[33 + 4 * i]), fu(oc[34 + 4 * i]), fu(oc[35 + 4 * i]));
  nb_sync(NB_RED, 256);
  const uint32_t ot = stg0 + warp * 2048;
#pragma unroll
  for (int i = 0; i < 8; i += 2) {
    const uint4 v0 = lds128(xi + i * 2048), v1 = lds128(xi + i * 2048 + 2048);
    stsm4(ot + (lane & 15) * 128 + (((i + (lane >> 4)) ^ (lane & 7)) << 4),
          pack_bf(oc[4 * i] + uf(v0.x), oc[4 * i + 1] + uf(v0.y)), pack_bf(oc[4 * i + 2] + uf(v0.z), oc[4 * i + 3] + uf(v0.w)),
          pack_bf(oc[4 * i + 4] + uf(v1.x), oc[4 * i + 5] + uf(v1.y)), pack_bf(oc[4 * i + 6] + uf(v1.z), oc[4 * i + 7] + uf(v1.w)));
  }
  asm volatile("fence.proxy.async.shared::cta;" ::: "memory");
  __syncwarp();
  e_store2d(&mout, ot, (hp & 3) * 128 + wg * 64, rb * 64 + w * 16);
  TS(wg * 16 + 11);
  GT(61 + wg);
}

typedef CUresult (*EncodeFn)(CUtensorMap*, CUtensorMapDataType, cuuint32_t, void*, const cuuint64_t*, const cuuint64_t*,
                             const cuuint32_t*, const cuuint32_t*, CUtensorMapInterleave, CUtensorMapSwizzle,
                             CUtensorMapL2promotion, CUtensorMapFloatOOBfill);

}

extern "C" void kernel_launch(void* const* d_in, const int* in_sizes, int n_in, void* d_out, int out_size) {
  (void)in_sizes; (void)n_in; (void)out_size;
  void* fn = nullptr;
  cudaDriverEntryPointQueryResult qr;
  cudaGetDriverEntryPoint("cuTensorMapEncodeTiled", &fn, cudaEnableDefault, &qr);
  EncodeFn enc = (EncodeFn)fn;
  CUtensorMap mx, mw, mo, mu, mout;
  const cuuint32_t es[5] = {1, 1, 1, 1, 1};
  {
    cuuint64_t dims[2] = {512, 2048}, st[1] = {1024};
    cuuint32_t box[2] = {64, 128};
    enc(&mx, CU_TENSOR_MAP_DATA_TYPE_BFLOAT16, 2, d_in[0], dims, st, box, es, CU_TENSOR_MAP_INTERLEAVE_NONE,
        CU_TENSOR_MAP_SWIZZLE_128B, CU_TENSOR_MAP_L2_PROMOTION_L2_128B, CU_TENSOR_MAP_FLOAT_OOB_FILL_NONE);
  }
  {
    cuuint64_t dims[3] = {512, 512, 3}, st[2] = {3072, 1024};
    cuuint32_t box[3] = {32, 64, 3};
    enc(&mw, CU_TENSOR_MAP_DATA_TYPE_BFLOAT16, 3, d_in[1], dims, st, box, es, CU_TENSOR_MAP_INTERLEAVE_NONE,
        CU_TENSOR_MAP_SWIZZLE_64B, CU_TENSOR_MAP_L2_PROMOTION_L2_128B, CU_TENSOR_MAP_FLOAT_OOB_FILL_NONE);
  }
  {
    cuuint64_t dims[2] = {512, 512}, st[1] = {1024};
    cuuint32_t box[2] = {64, 64};
    enc(&mo, CU_TENSOR_MAP_DATA_TYPE_BFLOAT16, 2, d_in[3], dims, st, box, es, CU_TENSOR_MAP_INTERLEAVE_NONE,
        CU_TENSOR_MAP_SWIZZLE_128B, CU_TENSOR_MAP_L2_PROMOTION_L2_128B, CU_TENSOR_MAP_FLOAT_OOB_FILL_NONE);
  }
  {
    cuuint64_t dims[5] = {512, 2, 4, 4, 64}, st[4] = {1024, 8192, 2048, 32768};
    cuuint32_t box[5] = {64, 2, 4, 4, 4};
    enc(&mu, CU_TENSOR_MAP_DATA_TYPE_BFLOAT16, 5, d_in[4], dims, st, box, es, CU_TENSOR_MAP_INTERLEAVE_NONE,
        CU_TENSOR_MAP_SWIZZLE_128B, CU_TENSOR_MAP_L2_PROMOTION_L2_128B, CU_TENSOR_MAP_FLOAT_OOB_FILL_NONE);
  }
  {
    cuuint64_t dims[2] = {1024, 2048}, st[1] = {2048};
    cuuint32_t box[2] = {64, 16};
    enc(&mout, CU_TENSOR_MAP_DATA_TYPE_BFLOAT16, 2, d_out, dims, st, box, es, CU_TENSOR_MAP_INTERLEAVE_NONE,
        CU_TENSOR_MAP_SWIZZLE_128B, CU_TENSOR_MAP_L2_PROMOTION_NONE, CU_TENSOR_MAP_FLOAT_OOB_FILL_NONE);
  }
  Params P;
  P.x = (const __nv_bfloat16*)d_in[0];
  P.wphi = (const __nv_bfloat16*)d_in[2];
  P.wo = (const __nv_bfloat16*)d_in[3];
  P.u = (const __nv_bfloat16*)d_in[4];
  P.logA = (const __nv_bfloat16*)d_in[5];
  P.Aim = (const __nv_bfloat16*)d_in[6];
  P.Cre = (const __nv_bfloat16*)d_in[7];
  P.Cim = (const __nv_bfloat16*)d_in[8];
  P.logdt = (const __nv_bfloat16*)d_in[9];
  P.Dskip = (const __nv_bfloat16*)d_in[10];
  P.out = (__nv_bfloat16*)d_out;
  cudaFuncSetAttribute(fused_kernel, cudaFuncAttributeMaxDynamicSharedMemorySize, SMEM_BYTES);
  fused_kernel<<<NCTA, NTHREADS, SMEM_BYTES>>>(P, mx, mw, mo, mu, mout);
}
```

```cpp
#include <cuda_runtime.h>
#include <cuda_bf16.h>
#include <cuda_fp16.h>
#include <cuda.h>
#include <stdint.h>

#define DBG_TS 0

namespace {

constexpr int NTHREADS = 512;
constexpr int NCTA = 128;
constexpr int OFF_W = 0;
constexpr int OFF_X = 98304;
constexpr int OFF_U = OFF_X + 65536;
constexpr int U_CH = 4416, U_ODD = 2240, U_PAD = 128;
constexpr int OFF_STG0 = OFF_U + 18432;
constexpr int OFF_T = OFF_STG0 + 24576;
constexpr int T_CH = 5216;
constexpr int T_D = 0;
constexpr int T_5 = 2144;
constexpr int T_3 = T_5 + 384;
constexpr int T_7 = T_5 + 1024;
constexpr int T_9 = T_7 + 320;
constexpr int T_KC = T_9 + 320;
constexpr int T_ST = T_5 - 1024;
constexpr int OFF_PHI = OFF_T + 4 * T_CH;
constexpr int OFF_BAR = OFF_PHI + 1024;
constexpr int SMEM_BYTES = OFF_BAR + 512;
constexpr uint32_t SB = 1024;
static_assert(T_KC + 2 * 656 <= T_CH, "table size");
static_assert(SMEM_BYTES <= 232448, "smem");
constexpr int MB_URAW = 0, MB_FULL = 1  , MB_WO = 17  , MB_UFULL = 19, MB_ZOK = 20,
              MB_EMPTY = 21  , MB_CLOSE = 37;
__host__ __device__ constexpr uint32_t BAR(int i) { return SB + OFF_BAR + 8 * i; }
constexpr int NB_WG0 = 1, NB_KPART = 2, NB_ST0 = 3  , NB_KV = 5, NB_RED = 6, NB_INIT = 7, NB_PREP = 8, NB_PROD = 9, NB_RDY = 10, NB_BDONE = 11, NB_ZERO = 12;
#define ZERO_N 1024
#define ZERO_STEP 3
#define STEPU 0
#define STEPPF 0
constexpr int STEP_PF = STEPPF, STEP_U = STEPU;
constexpr int SPIN_MAX = 1 << 16;

__device__ unsigned g_cnt[9 * 32];
__device__ uint4 g_uT[512 * 256];
__device__ uint4 g_part[16 * 8 * 144];
__device__ uint4 g_o[32 * 32 * 128];
__device__ uint4 g_y[512 * 8 * 32];
extern __shared__ uint8_t smem_raw[];
#define TS(i) do {} while (0)
#define TS1(i) do {} while (0)
#define GT(i) do {} while (0)

__device__ __forceinline__ uint32_t smem_u32(const void* p) { return (uint32_t)__cvta_generic_to_shared(p); }
__device__ __forceinline__ void mbar_arrive(uint32_t b) {
  asm volatile("mbarrier.arrive.shared::cta.b64 _, [%0];" ::"r"(b) : "memory");
}
__device__ __forceinline__ void mbar_wait(uint32_t b) {
  uint32_t done = 0;
#pragma unroll 1
  for (int i = 0; i < SPIN_MAX && !done; i++) {
    asm volatile("{\n.reg .pred p;\nmbarrier.try_wait.parity.shared::cta.b64 p, [%1], 0, 4000;\nselp.u32 %0, 1, 0, p;\n}\n"
                 : "=r"(done) : "r"(b) : "memory");
  }
}
__device__ __forceinline__ void mbar_init(uint32_t b, int n) {
  asm volatile("mbarrier.init.shared::cta.b64 [%0], %1;" ::"r"(b), "r"(n) : "memory");
}
__device__ __forceinline__ void mbar_expect(uint32_t b, int bytes) {
  asm volatile("mbarrier.arrive.expect_tx.shared::cta.b64 _, [%0], %1;" ::"r"(b), "r"(bytes) : "memory");
}
__device__ __forceinline__ void nb_sync(int id, int n) { asm volatile("bar.sync %0, %1;" ::"r"(id), "r"(n) : "memory"); }
__device__ __forceinline__ void nb_arrive(int id, int n) { asm volatile("bar.arrive %0, %1;" ::"r"(id), "r"(n) : "memory"); }
#define ELECT "{\n.reg .pred p;\nelect.sync _|p, 0xffffffff;\n@p "
__device__ __forceinline__ void e_expect(uint32_t b, int bytes) {
  asm volatile(ELECT "mbarrier.arrive.expect_tx.shared::cta.b64 _, [%0], %1;\n}\n" ::"r"(b), "r"(bytes) : "memory");
}
__device__ __forceinline__ void e_tma2d(uint32_t dst, const CUtensorMap* m, uint32_t bar, int c0, int c1) {
  asm volatile(ELECT "cp.async.bulk.tensor.2d.shared::cluster.global.mbarrier::complete_tx::bytes [%0], [%1, {%3,%4}], [%2];\n}\n"
               ::"r"(dst), "l"(m), "r"(bar), "r"(c0), "r"(c1) : "memory");
}
__device__ __forceinline__ void e_tma3d(uint32_t dst, const CUtensorMap* m, uint32_t bar, int c0, int c1, int c2) {
  asm volatile(ELECT "cp.async.bulk.tensor.3d.shared::cluster.global.mbarrier::complete_tx::bytes [%0], [%1, {%3,%4,%5}], [%2];\n}\n"
               ::"r"(dst), "l"(m), "r"(bar), "r"(c0), "r"(c1), "r"(c2) : "memory");
}
__device__ __forceinline__ void e_tma5d(uint32_t dst, const CUtensorMap* m, uint32_t bar, int c0, int c4) {
  asm volatile(ELECT "cp.async.bulk.tensor.5d.shared::cluster.global.mbarrier::complete_tx::bytes [%0], [%1, {%3,%5,%5,%5,%4}], [%2];\n}\n"
               ::"r"(dst), "l"(m), "r"(bar), "r"(c0), "r"(c4), "r"(0) : "memory");
}
__device__ __forceinline__ void e_bulk(uint32_t dst, const void* src, int bytes, uint32_t bar) {
  asm volatile(ELECT "cp.async.bulk.shared::cluster.global.mbarrier::complete_tx::bytes [%0], [%1], %2, [%3];\n}\n"
               ::"r"(dst), "l"(src), "r"(bytes), "r"(bar) : "memory");
}
__device__ __forceinline__ void e_prefetch(const void* p, int bytes) {
  asm volatile(ELECT "cp.async.bulk.prefetch.L2.global [%0], %1;\n}\n" ::"l"(p), "r"(bytes) : "memory");
}
__device__ __forceinline__ void e_store2d(const CUtensorMap* m, uint32_t src, int c0, int c1) {
  asm volatile(ELECT "cp.async.bulk.tensor.2d.global.shared::cta.bulk_group [%0, {%2,%3}], [%1];\n"
               "@p cp.async.bulk.commit_group;\n@p cp.async.bulk.wait_group.read 0;\n}\n"
               ::"l"(m), "r"(src), "r"(c0), "r"(c1) : "memory");
}
__host__ __device__ constexpr uint64_t mkdesc(uint32_t addr, uint32_t lbo, uint32_t sbo, int swz) {
  return (uint64_t)((addr & 0x3FFFF) >> 4) | ((uint64_t)(lbo >> 4) << 16) | ((uint64_t)(sbo >> 4) << 32) |
         ((uint64_t)swz << 62);
}
#define WG_FENCE() asm volatile("wgmma.fence.sync.aligned;" ::: "memory")
#define WG_COMMIT() asm volatile("wgmma.commit_group.sync.aligned;" ::: "memory")
#define WG_WAIT(n) asm volatile("wgmma.wait_group.sync.aligned " #n ";" ::: "memory")

__device__ __forceinline__ void mma(float& d0, float& d1, float& d2, float& d3, uint32_t a0, uint32_t a1, uint32_t a2,
                                    uint32_t a3, uint32_t b0, uint32_t b1) {
  asm volatile("mma.sync.aligned.m16n8k16.row.col.f32.bf16.bf16.f32 {%0,%1,%2,%3},{%4,%5,%6,%7},{%8,%9},{%0,%1,%2,%3};"
               : "+f"(d0), "+f"(d1), "+f"(d2), "+f"(d3)
               : "r"(a0), "r"(a1), "r"(a2), "r"(a3), "r"(b0), "r"(b1));
}
__device__ __forceinline__ void mmac(float (&d)[4], uint32_t a0, uint32_t a1, uint32_t a2, uint32_t a3, uint32_t b0,
                                     uint32_t b1, const float (&c)[4]) {
  asm volatile("mma.sync.aligned.m16n8k16.row.col.f32.bf16.bf16.f32 {%0,%1,%2,%3},{%4,%5,%6,%7},{%8,%9},{%10,%11,%12,%13};"
               : "=f"(d[0]), "=f"(d[1]), "=f"(d[2]), "=f"(d[3])
               : "r"(a0), "r"(a1), "r"(a2), "r"(a3), "r"(b0), "r"(b1), "f"(c[0]), "f"(c[1]), "f"(c[2]), "f"(c[3]));
}
__device__ __forceinline__ void mma_p(int p, float (&d)[4], uint32_t a0, uint32_t a1, uint32_t a2, uint32_t a3, uint32_t b0, uint32_t b1) {
  asm volatile("{\n.reg .pred q;\nsetp.ne.b32 q, %10, 0;\n"
               "@q mma.sync.aligned.m16n8k16.row.col.f32.bf16.bf16.f32 {%0,%1,%2,%3},{%4,%5,%6,%7},{%8,%9},{%0,%1,%2,%3};\n}\n"
               : "+f"(d[0]), "+f"(d[1]), "+f"(d[2]), "+f"(d[3])
               : "r"(a0), "r"(a1), "r"(a2), "r"(a3), "r"(b0), "r"(b1), "r"(p));
}
__device__ __forceinline__ void mmac_p(int p, float (&d)[4], uint32_t a0, uint32_t a1, uint32_t a2, uint32_t a3, uint32_t b0,
                                       uint32_t b1, const float (&c)[4]) {
  asm volatile("{\n.reg .pred q;\nsetp.ne.b32 q, %14, 0;\n"
               "@q mma.sync.aligned.m16n8k16.row.col.f32.bf16.bf16.f32 {%0,%1,%2,%3},{%4,%5,%6,%7},{%8,%9},{%10,%11,%12,%13};\n}\n"
               : "+f"(d[0]), "+f"(d[1]), "+f"(d[2]), "+f"(d[3])
               : "r"(a0), "r"(a1), "r"(a2), "r"(a3), "r"(b0), "r"(b1), "f"(c[0]), "f"(c[1]), "f"(c[2]), "f"(c[3]), "r"(p));
}
__device__ __forceinline__ void mma_k8(float (&d)[4], uint32_t a0, uint32_t a1, uint32_t b0) {
  asm volatile("mma.sync.aligned.m16n8k8.row.col.f32.bf16.bf16.f32 {%0,%1,%2,%3},{%4,%5},{%6},{%0,%1,%2,%3};"
               : "+f"(d[0]), "+f"(d[1]), "+f"(d[2]), "+f"(d[3]) : "r"(a0), "r"(a1), "r"(b0));
}
__device__ __forceinline__ void mma0(float& d0, float& d1, float& d2, float& d3, uint32_t a0, uint32_t a1, uint32_t a2,
                                     uint32_t a3, uint32_t b0, uint32_t b1) {
  asm volatile("mma.sync.aligned.m16n8k16.row.col.f32.bf16.bf16.f32 {%0,%1,%2,%3},{%4,%5,%6,%7},{%8,%9},{%10,%10,%10,%10};"
               : "=f"(d0), "=f"(d1), "=f"(d2), "=f"(d3)
               : "r"(a0), "r"(a1), "r"(a2), "r"(a3), "r"(b0), "r"(b1), "f"(0.f));
}
__device__ __forceinline__ uint32_t pack_bf(float lo, float hi) {
  uint32_t r;
  asm("cvt.rn.bf16x2.f32 %0, %1, %2;" : "=r"(r) : "f"(hi), "f"(lo));
  return r;
}
__device__ __forceinline__ float bf_lo(uint32_t w) { return __uint_as_float(w << 16); }
__device__ __forceinline__ float bf_hi(uint32_t w) { return __uint_as_float(w & 0xffff0000u); }
__device__ __forceinline__ float bf_round(float x) { return __bfloat162float(__float2bfloat16_rn(x)); }
__device__ __forceinline__ uint32_t bmax2(uint32_t a, uint32_t b) {
  uint32_t r; asm("max.bf16x2 %0, %1, %2;" : "=r"(r) : "r"(a), "r"(b)); return r;
}
__device__ __forceinline__ uint32_t bmin2(uint32_t a, uint32_t b) {
  uint32_t r; asm("min.bf16x2 %0, %1, %2;" : "=r"(r) : "r"(a), "r"(b)); return r;
}
__device__ __forceinline__ float ex2(float x) { float r; asm("ex2.approx.ftz.f32 %0, %1;" : "=f"(r) : "f"(x)); return r; }
__device__ __forceinline__ float rcp(float x) { float r; asm("rcp.approx.ftz.f32 %0, %1;" : "=f"(r) : "f"(x)); return r; }
__device__ __forceinline__ void ldsm4(uint32_t (&r)[4], uint32_t a) {
  asm volatile("ldmatrix.sync.aligned.m8n8.x4.shared.b16 {%0,%1,%2,%3}, [%4];"
               : "=r"(r[0]), "=r"(r[1]), "=r"(r[2]), "=r"(r[3]) : "r"(a) : "memory");
}
__device__ __forceinline__ void ldsm4t(uint32_t (&r)[4], uint32_t a) {
  asm volatile("ldmatrix.sync.aligned.m8n8.x4.trans.shared.b16 {%0,%1,%2,%3}, [%4];"
               : "=r"(r[0]), "=r"(r[1]), "=r"(r[2]), "=r"(r[3]) : "r"(a) : "memory");
}
__device__ __forceinline__ void stsm4(uint32_t a, uint32_t r0, uint32_t r1, uint32_t r2, uint32_t r3) {
  asm volatile("stmatrix.sync.aligned.m8n8.x4.shared.b16 [%0], {%1,%2,%3,%4};"
               ::"r"(a), "r"(r0), "r"(r1), "r"(r2), "r"(r3) : "memory");
}
__device__ __forceinline__ uint32_t lds32(uint32_t a) {
  uint32_t r; asm volatile("ld.shared.u32 %0, [%1];" : "=r"(r) : "r"(a) : "memory"); return r;
}
__device__ __forceinline__ uint32_t lds16(uint32_t a) {
  uint32_t r; asm volatile("{\n.reg .u16 h;\nld.shared.u16 h, [%1];\ncvt.u32.u16 %0, h;\n}\n" : "=r"(r) : "r"(a) : "memory"); return r;
}
__device__ __forceinline__ uint2 lds64(uint32_t a) {
  uint2 r; asm volatile("ld.shared.v2.u32 {%0,%1}, [%2];" : "=r"(r.x), "=r"(r.y) : "r"(a) : "memory"); return r;
}
__device__ __forceinline__ uint4 lds128(uint32_t a) {
  uint4 r;
  asm volatile("ld.shared.v4.u32 {%0,%1,%2,%3}, [%4];" : "=r"(r.x), "=r"(r.y), "=r"(r.z), "=r"(r.w) : "r"(a) : "memory");
  return r;
}
__device__ __forceinline__ void sts32(uint32_t a, uint32_t v) { asm volatile("st.shared.u32 [%0], %1;" ::"r"(a), "r"(v) : "memory"); }
__device__ __forceinline__ void sts16(uint32_t a, uint32_t v) {
  asm volatile("{\n.reg .u16 h;\ncvt.u16.u32 h, %1;\nst.shared.u16 [%0], h;\n}\n" ::"r"(a), "r"(v) : "memory");
}
__device__ __forceinline__ void sts64(uint32_t a, uint32_t x, uint32_t y) {
  asm volatile("st.shared.v2.u32 [%0], {%1,%2};" ::"r"(a), "r"(x), "r"(y) : "memory");
}
__device__ __forceinline__ void sts128(uint32_t a, uint32_t x, uint32_t y, uint32_t z, uint32_t w) {
  asm volatile("st.shared.v4.u32 [%0], {%1,%2,%3,%4};" ::"r"(a), "r"(x), "r"(y), "r"(z), "r"(w) : "memory");
}
__device__ __forceinline__ uint4 ld_x(const uint4* p) {
  uint4 r;
  asm volatile("{\n.reg .b128 t;\nld.relaxed.gpu.global.b128 t, [%4];\nmov.b128 {%0,%1,%2,%3}, t;\n}\n"
               : "=r"(r.x), "=r"(r.y), "=r"(r.z), "=r"(r.w) : "l"(p) : "memory");
  return r;
}
__device__ __forceinline__ uint32_t ld_x32(const uint32_t* p) {
  uint32_t r; asm volatile("ld.relaxed.gpu.global.u32 %0, [%1];" : "=r"(r) : "l"(p) : "memory"); return r;
}
__device__ __forceinline__ void st_x(uint4* p, uint32_t x, uint32_t y, uint32_t z, uint32_t w) {
  asm volatile("{\n.reg .b128 t;\nmov.b128 t, {%1,%2,%3,%4};\nst.relaxed.gpu.global.b128 [%0], t;\n}\n"
               ::"l"(p), "r"(x), "r"(y), "r"(z), "r"(w) : "memory");
}
__device__ __forceinline__ void st_x_p(int p, uint4* a, uint32_t x, uint32_t y, uint32_t z, uint32_t w) {
  asm volatile("{\n.reg .b128 t;\n.reg .pred q;\nsetp.ne.b32 q, %5, 0;\nmov.b128 t, {%1,%2,%3,%4};\n@q st.relaxed.gpu.global.b128 [%0], t;\n}\n"
               ::"l"(a), "r"(x), "r"(y), "r"(z), "r"(w), "r"(p) : "memory");
}
__device__ __forceinline__ void sts64_p(int p, uint32_t a, uint32_t x, uint32_t y) {
  asm volatile("{\n.reg .pred q;\nsetp.ne.b32 q, %3, 0;\n@q st.shared.v2.u32 [%0], {%1,%2};\n}\n" ::"r"(a), "r"(x), "r"(y), "r"(p) : "memory");
}
__device__ __forceinline__ void st_x32(uint32_t* p, uint32_t x) {
  asm volatile("st.relaxed.gpu.global.u32 [%0], %1;" ::"l"(p), "r"(x) : "memory");
}
__device__ __forceinline__ uint32_t nz(uint32_t w) { return max(w, 1u); }
__device__ __forceinline__ uint32_t fu(float x) { return __float_as_uint(x); }
__device__ __forceinline__ float uf(uint32_t x) { return __uint_as_float(x); }

__device__ __forceinline__ void wgmma_ss_n96(float (&d)[48], uint64_t da, uint64_t db, int sc) {
  asm volatile("{\n.reg .pred p;\nsetp.ne.b32 p, %50, 0;\n"
      "wgmma.mma_async.sync.aligned.m64n96k16.f32.bf16.bf16 "
      "{%0,%1,%2,%3,%4,%5,%6,%7,%8,%9,%10,%11,%12,%13,%14,%15,%16,%17,%18,%19,%20,%21,%22,%23,%24,%25,%26,%27,%28,%29,%30,%31,%32,%33,%34,%35,%36,%37,%38,%39,%40,%41,%42,%43,%44,%45,%46,%47}, "
      "%48, %49, p, 1, 1, 0, 1;\n}\n"
      : "+f"(d[0]), "+f"(d[1]), "+f"(d[2]), "+f"(d[3]), "+f"(d[4]), "+f"(d[5]), "+f"(d[6]), "+f"(d[7]),
        "+f"(d[8]), "+f"(d[9]), "+f"(d[10]), "+f"(d[11]), "+f"(d[12]), "+f"(d[13]), "+f"(d[14]), "+f"(d[15]),
        "+f"(d[16]), "+f"(d[17]), "+f"(d[18]), "+f"(d[19]), "+f"(d[20]), "+f"(d[21]), "+f"(d[22]), "+f"(d[23]),
        "+f"(d[24]), "+f"(d[25]), "+f"(d[26]), "+f"(d[27]), "+f"(d[28]), "+f"(d[29]), "+f"(d[30]), "+f"(d[31]),
        "+f"(d[32]), "+f"(d[33]), "+f"(d[34]), "+f"(d[35]), "+f"(d[36]), "+f"(d[37]), "+f"(d[38]), "+f"(d[39]),
        "+f"(d[40]), "+f"(d[41]), "+f"(d[42]), "+f"(d[43]), "+f"(d[44]), "+f"(d[45]), "+f"(d[46]), "+f"(d[47])
      : "l"(da), "l"(db), "r"(sc));
}

__device__ __forceinline__ void wgmma_rs_n128(float (&d)[64], const uint4& a, uint64_t db, int sc) {
  asm volatile("{\n.reg .pred p;\nsetp.ne.b32 p, %69, 0;\n"
      "wgmma.mma_async.sync.aligned.m64n128k16.f32.bf16.bf16 "
      "{%0,%1,%2,%3,%4,%5,%6,%7,%8,%9,%10,%11,%12,%13,%14,%15,%16,%17,%18,%19,%20,%21,%22,%23,%24,%25,%26,%27,%28,%29,%30,%31,%32,%33,%34,%35,%36,%37,%38,%39,%40,%41,%42,%43,%44,%45,%46,%47,%48,%49,%50,%51,%52,%53,%54,%55,%56,%57,%58,%59,%60,%61,%62,%63}, "
      "{%64,%65,%66,%67}, %68, p, 1, 1, 1;\n}\n"
      : "+f"(d[0]), "+f"(d[1]), "+f"(d[2]), "+f"(d[3]), "+f"(d[4]), "+f"(d[5]), "+f"(d[6]), "+f"(d[7]),
        "+f"(d[8]), "+f"(d[9]), "+f"(d[10]), "+f"(d[11]), "+f"(d[12]), "+f"(d[13]), "+f"(d[14]), "+f"(d[15]),
        "+f"(d[16]), "+f"(d[17]), "+f"(d[18]), "+f"(d[19]), "+f"(d[20]), "+f"(d[21]), "+f"(d[22]), "+f"(d[23]),
        "+f"(d[24]), "+f"(d[25]), "+f"(d[26]), "+f"(d[27]), "+f"(d[28]), "+f"(d[29]), "+f"(d[30]), "+f"(d[31]),
        "+f"(d[32]), "+f"(d[33]), "+f"(d[34]), "+f"(d[35]), "+f"(d[36]), "+f"(d[37]), "+f"(d[38]), "+f"(d[39]),
        "+f"(d[40]), "+f"(d[41]), "+f"(d[42]), "+f"(d[43]), "+f"(d[44]), "+f"(d[45]), "+f"(d[46]), "+f"(d[47]),
        "+f"(d[48]), "+f"(d[49]), "+f"(d[50]), "+f"(d[51]), "+f"(d[52]), "+f"(d[53]), "+f"(d[54]), "+f"(d[55]),
        "+f"(d[56]), "+f"(d[57]), "+f"(d[58]), "+f"(d[59]), "+f"(d[60]), "+f"(d[61]), "+f"(d[62]), "+f"(d[63])
      : "r"(a.x), "r"(a.y), "r"(a.z), "r"(a.w), "l"(db), "r"(sc));
}

struct Params {
  const __nv_bfloat16 *x, *wphi, *wo, *u, *logA, *Aim, *Cre, *Cim, *logdt, *Dskip;
  __nv_bfloat16* out;
};

__device__ __forceinline__ uint4 tr_row(const uint4 (&v)[8], int i) {
  uint32_t o[4];
#pragma unroll
  for (int m = 0; m < 4; m++) {
    const uint4 &ra = v[2 * m], &rb = v[2 * m + 1];
    const int k = i >> 1;
    const uint32_t xa = k == 0 ? ra.x : k == 1 ? ra.y : k == 2 ? ra.z : ra.w;
    const uint32_t xb = k == 0 ? rb.x : k == 1 ? rb.y : k == 2 ? rb.z : rb.w;
    o[m] = __byte_perm(xa, xb, (i & 1) ? 0x7632 : 0x5410);
  }
  return make_uint4(o[0], o[1], o[2], o[3]);
}

struct cpx { float r, i; };
__device__ __forceinline__ cpx cmul(cpx a, cpx b) { return {a.r * b.r - a.i * b.i, a.r * b.i + a.i * b.r}; }
__device__ __forceinline__ cpx csq(cpx a) { return {a.r * a.r - a.i * a.i, 2.f * (a.r * a.i)}; }
__device__ __forceinline__ cpx polar(float e, float t) {
  const float m = ex2(e);
  return {m * __cosf(t), m * __sinf(t)};
}

struct KgenRaw { unsigned short la, ai, cr, ci, ldt; };
__device__ __forceinline__ KgenRaw kgen_load(const Params& P, int d, int unit, int lane) {
  const int o = d * 128 + unit * 32 + lane;
  return {__ldg((const unsigned short*)P.logA + o), __ldg((const unsigned short*)P.Aim + o), __ldg((const unsigned short*)P.Cre + o),
          __ldg((const unsigned short*)P.Cim + o), __ldg((const unsigned short*)P.logdt + d)};
}
__device__ __forceinline__ void kgen_unit(const KgenRaw& r, int lane, uint32_t buf, uint32_t open_bar, float& dt,
                                          float (&k)[5][4], float& k2048) {
  dt = bf_round(expf(bf_lo(r.ldt)));
  const float a2 = -(bf_round(expf(bf_lo(r.la))) * dt) * 1.4426950408889634f;
  const float f = bf_lo(r.ai) * dt;
  const float r128 = f * 20.371832715762604f;
  const cpx C = {bf_lo(r.cr), -bf_lo(r.ci)};
  const uint32_t sa = buf + (lane & 7) * 128 + ((((lane >> 3) ^ lane) & 7) << 4);
  const uint32_t lb = buf + (lane >> 3) * 128 + (((lane ^ (lane >> 3)) & 7) << 4);
  const uint32_t la = buf + ((lane >> 3) & 1) * 1024 + (lane >> 4) * 128 + (((lane ^ (lane >> 4)) & 7) << 4);
  auto put = [&](const cpx (&v)[8], uint32_t off) {
    stsm4(sa + off, pack_bf(v[0].r, v[0].i), pack_bf(v[1].r, v[1].i), pack_bf(v[2].r, v[2].i), pack_bf(v[3].r, v[3].i));
    stsm4((sa ^ 64) + off, pack_bf(v[4].r, v[4].i), pack_bf(v[5].r, v[5].i), pack_bf(v[6].r, v[6].i), pack_bf(v[7].r, v[7].i));
  };
  uint32_t A[4][4], B[5][2][4];
  auto getB = [&](int j, uint32_t off) {
    __syncwarp();
    ldsm4(B[j][0], lb + off);
    ldsm4(B[j][1], (lb ^ 64) + 512 + off);
  };
  cpx t0[8], t1[8], t2[8], t3[8], t4[8];
  t0[0] = {1.f, 0.f};
  t0[1] = polar(a2, f);
  t1[0] = polar(a2 * 128.f, (r128 - rintf(r128)) * 6.283185307179586f);
  t0[2] = csq(t0[1]); t0[4] = csq(t0[2]);
  t2[0] = csq(t1[0]); t3[0] = csq(t2[0]); t4[0] = csq(t3[0]);
  t0[3] = cmul(t0[2], t0[1]); t0[5] = cmul(t0[4], t0[1]); t0[6] = cmul(t0[4], t0[2]); t0[7] = cmul(t0[4], t0[3]);
  put(t0, 0); getB(0, 0);
  {
    cpx w8 = csq(t0[4]);
    w8.i = -w8.i;
    const cpx w16 = csq(w8), w32 = csq(w16), w64 = csq(w32);
    cpx a[8];
    a[0] = C; a[1] = cmul(C, w8);
    a[2] = cmul(a[0], w16); a[3] = cmul(a[1], w16);
#pragma unroll
    for (int i = 0; i < 4; i++) a[4 + i] = cmul(a[i], w32);
    put(a, 0);
#pragma unroll
    for (int i = 0; i < 8; i++) a[i] = cmul(a[i], w64);
    put(a, 1024);
    __syncwarp();
#pragma unroll
    for (int s = 0; s < 4; s++) ldsm4(A[s], (la ^ (s << 5)) + s * 256);
  }
#pragma unroll
  for (int i = 1; i < 8; i++) t1[i] = cmul(t0[i], t1[0]);
  put(t1, 0); getB(1, 0);
#pragma unroll
  for (int i = 1; i < 8; i++) t2[i] = cmul((i & 1) ? t1[i & 6] : t0[i & 6], t2[0]);
  put(t2, 1024); getB(2, 1024);
#pragma unroll
  for (int i = 1; i < 8; i++) t3[i] = cmul((i & 2) ? t2[i & 5] : ((i & 1) ? t1[i & 4] : t0[i & 4]), t3[0]);
  put(t3, 0); getB(3, 0);
#pragma unroll
  for (int i = 1; i < 8; i++) t4[i] = cmul((i & 4) ? t3[i & 3] : ((i & 2) ? t2[i & 1] : t1[0]), t4[0]);
  put(t4, 1024); getB(4, 1024);
  const cpx we = csq(t4[0]);
  k2048 += C.r * we.r + C.i * we.i;
  if (open_bar) mbar_wait(open_bar);
#pragma unroll
  for (int s = 0; s < 4; s++)
#pragma unroll
    for (int j = 0; j < 5; j++)
      mma(k[j][0], k[j][1], k[j][2], k[j][3], A[s][0], A[s][1], A[s][2], A[s][3], B[j][s >> 1][2 * (s & 1)], B[j][s >> 1][2 * (s & 1) + 1]);
}

__device__ __forceinline__ void build_tables(uint32_t tb, int lane, float (&k)[5][4], float k2048) {
  const int g = lane >> 2, c = lane & 3;
  const uint32_t kc = tb + T_KC + 16;
  {
    const uint32_t a0 = kc + 16 * g + 4 * c, a2 = kc + 2 * (256 + 4 * g + c);
    const uint32_t a3 = kc + 2 * (384 + 2 * g + 64 * (c & 1) + (c >> 1)), a4 = kc + 2 * (512 + g + 32 * c);
#pragma unroll
    for (int r = 0; r < 2; r++) {
      sts32(a0 + 128 * r, pack_bf(k[0][2 * r], k[0][2 * r + 1]));
      sts32(a0 + 128 * r + 256, pack_bf(k[1][2 * r], k[1][2 * r + 1]));
      const uint32_t w2 = pack_bf(k[2][2 * r], k[2][2 * r + 1]);
      const uint32_t w3 = pack_bf(k[3][2 * r], k[3][2 * r + 1]);
      const uint32_t w4 = pack_bf(k[4][2 * r], k[4][2 * r + 1]);
      sts16(a2 + 64 * r, w2); sts16(a2 + 64 * r + 128, w2 >> 16);
      sts16(a3 + 32 * r, w3); sts16(a3 + 32 * r + 64, w3 >> 16);
      sts16(a4 + 16 * r, w4); sts16(a4 + 16 * r + 32, w4 >> 16);
    }
  }
  if (lane == 0) { sts16(kc + 2 * 640, pack_bf(k2048, 0.f)); sts16(kc - 2, 0); }
  __syncwarp();
  const uint32_t td = tb + T_D + 32;
  {
    const uint4 v = lds128(kc + 16 * lane);
    const uint32_t pv = lds16(kc + 16 * lane - 2);
    sts128(td + 32 * lane, __byte_perm(v.x, pv, 0x5410), __byte_perm(v.x, v.x, 0x1032), __byte_perm(v.y, v.x, 0x7610),
           __byte_perm(v.y, v.y, 0x1032));
    sts128(td + 32 * lane + 16, __byte_perm(v.z, v.y, 0x7610), __byte_perm(v.z, v.z, 0x1032),
           __byte_perm(v.w, v.z, 0x7610), __byte_perm(v.w, v.w, 0x1032));
  }
  {
    const uint2 v = lds64(kc + 512 + 8 * lane);
    const uint32_t k4 = lds16(kc + 512 + 8 * lane + 8);
    const uint32_t pv = lds16(kc + (lane == 0 ? 510 : 512 + 8 * lane));
    const uint32_t k22 = __byte_perm(v.y, v.y, 0x1010);
    sts128(td + 1024 + 32 * lane, __byte_perm(v.x, pv, 0x5410), __byte_perm(v.x, v.x, 0x1010),
           __byte_perm(v.x, v.x, 0x1032), __byte_perm(v.y, v.x, 0x7610));
    sts128(td + 1024 + 32 * lane + 16, k22, k22, __byte_perm(v.y, v.y, 0x1032), __byte_perm(k4, v.y, 0x7610));
  }
  {
    const uint32_t kk = lds16(kc + 2 * 384);
    const uint32_t w = lane < 3 ? (kk | (kk << 16)) : (lane == 3 ? (kk << 16) : 0u);
    if (lane < 24) sts32(td + 4 * (lane < 16 ? 512 + lane : lane - 24), w);
    const uint32_t lo_ = lds16(kc + 2 * 511), le_ = lds16(kc + 2 * 512);
    const uint32_t ja = tb + T_5 + (lane < 16 ? 4 * lane : 256 + 4 * lane);
    sts32(ja, lane == 16 ? (le_ << 16) : 0u);
    sts32(ja + 384, lane == 16 ? (lo_ << 16) : 0u);
    sts32(tb + (lane < 16 ? T_7 : T_9 - 64) + 4 * lane, 0u);
  }
#pragma unroll
  for (int s = 0; s < 2; s++) {
    const uint32_t b = kc + 2 * (s ? 512 : 384) + 8 * lane;
    const uint2 v = lds64(b);
    uint32_t em = lds16(b - 2), e0 = v.x;
    const uint32_t e4 = lds16(b + 8);
    if (lane == 0) { em = 0; e0 = 0; }
    sts64(tb + (s ? T_7 : T_3) + 64 + 8 * lane, __byte_perm(v.x, em, 0x5432), __byte_perm(v.y, v.x, 0x7632));
    sts64(tb + (s ? T_9 : T_5) + 64 + 8 * lane, __byte_perm(v.y, e0, 0x5410), __byte_perm(e4, v.y, 0x5410));
  }
  __syncwarp();
}

__device__ __forceinline__ uint32_t box2w(int lo, int n, int o) {
  return ((unsigned)(o - lo) < (unsigned)n ? 0x3F80u : 0u) | ((unsigned)(o + 1 - lo) < (unsigned)n ? 0x3F800000u : 0u);
}

__device__ __forceinline__ void conv_channel(uint32_t ub, uint32_t tb, int lane, uint4* ydst) {
  const int g = lane >> 2, c = lane & 3, x = g - 2 * c;
  const uint32_t st = tb + T_ST + lane * 8;
  const int mi = lane >> 3;
  const uint32_t qa = ub + U_PAD + 16 * (lane & 7) + ((mi == 0 || mi == 3) ? U_ODD : 0) - (mi == 0 ? 16 : 0);
  const uint32_t kv = lds16(tb + T_KC + 16 + 2 * 512);
  {
    const uint32_t hb = ub + U_PAD + (mi & 1) * U_ODD + 16 * ((lane >> 4) + (lane & 7)) - 16;
    const int oh = c < 2 ? 8 + 2 * c : 2 * c - 8;
    const uint32_t bx0 = box2w(g - 4, 9, 2 * c), bx1 = box2w(g - 3, 7, 2 * c), bx2 = box2w(g - 4, 9, oh), bx3 = box2w(g - 3, 7, oh);
    uint32_t f7[9], f9a[9], f9b[9];
    const uint32_t fa = tb + T_7 + 4 * (8 + x);
#pragma unroll
    for (int m = 0; m < 9; m++) {
      f7[m] = lds32(fa + 32 * m);
      f9b[m] = lds32(fa + 320 + 32 * m);
      f9a[m] = lds32(fa + 316 + 32 * m);
    }
    mbar_wait(BAR(MB_EMPTY + 15));
    TS(36);
    uint32_t z09[8], z07[8], zm9[8], zm7[8];
#pragma unroll
    for (int i = 0; i < 8; i++) {
      uint32_t h[4];
      ldsm4(h, hb + 128 * i);
      float y0, y1, y2, y3, w0, w1, w2, w3;
      mma0(y0, y1, y2, y3, bx0, bx1, bx2, bx3, h[2], c < 2 ? h[3] : h[1]);
      mma0(w0, w1, w2, w3, bx0, bx1, bx2, bx3, h[1], c < 2 ? h[2] : h[0]);
      z09[i] = pack_bf(y0, y1); z07[i] = pack_bf(y2, y3);
      zm9[i] = pack_bf(w0, w1); zm7[i] = pack_bf(w2, w3);
    }
    float a[4][2][4];
#pragma unroll
    for (int kap = 0; kap < 4; kap++)
#pragma unroll
      for (int sg = 0; sg < 2; sg++)
#pragma unroll
        for (int bk = 3; bk >= kap; bk--) {
          const int m = 2 * (bk - kap) + 1;
          float(&a0)[4] = a[bk][0];
          float(&a1)[4] = a[bk][1];
          if (sg == 0 && kap == 0) {
            mma0(a0[0], a0[1], a0[2], a0[3], f9a[m], f9a[m + 1], f9a[m - 1], f9a[m], z09[0], z09[1]);
            mma0(a1[0], a1[1], a1[2], a1[3], f9b[m], f9b[m + 1], f9b[m - 1], f9b[m], zm9[0], zm9[1]);
          } else if (sg == 0) {
            mma(a0[0], a0[1], a0[2], a0[3], f9a[m], f9a[m + 1], f9a[m - 1], f9a[m], z09[2 * kap], z09[2 * kap + 1]);
            mma(a1[0], a1[1], a1[2], a1[3], f9b[m], f9b[m + 1], f9b[m - 1], f9b[m], zm9[2 * kap], zm9[2 * kap + 1]);
          } else {
            mma(a0[0], a0[1], a0[2], a0[3], f7[m], f7[m + 1], f7[m - 1], f7[m], zm7[2 * kap], zm7[2 * kap + 1]);
            mma(a1[0], a1[1], a1[2], a1[3], f7[m], f7[m + 1], f7[m - 1], f7[m], z07[2 * kap], z07[2 * kap + 1]);
          }
        }
#pragma unroll
    for (int bk = 0; bk < 4; bk++) {
      sts64(st + 256 * (8 + 2 * bk), pack_bf(a[bk][0][0], a[bk][0][1]), pack_bf(a[bk][1][0], a[bk][1][1]));
      sts64(st + 256 * (9 + 2 * bk), pack_bf(a[bk][0][2], a[bk][0][3]), pack_bf(a[bk][1][2], a[bk][1][3]));
    }
  }
  TS(44);
  {
    const int oh = c < 3 ? 2 * c : -10;
    const uint32_t bx0 = box2w(g - 10, 5, 2 * c - 8), bx1 = box2w(g - 5, 3, 2 * c - 8), bx2 = box2w(g - 10, 5, oh), bx3 = box2w(g - 5, 3, oh);
    const uint32_t lb0 = ((unsigned)(x + 5) < 2u ? kv : 0u) | ((unsigned)(x + 4) < 2u ? kv << 16 : 0u);
    const uint32_t lb1 = ((unsigned)(x - 3) < 2u ? kv : 0u) | ((unsigned)(x - 4) < 2u ? kv << 16 : 0u);
    const int q0 = g - 1, q1 = c < 3 ? g : g - 2;
    uint32_t y0a = ub + U_PAD + (q0 & 1) * U_ODD + 16 * (q0 >> 1) + 4 * c;
    uint32_t y1a = ub + U_PAD + (q1 & 1) * U_ODD + 16 * (q1 >> 1) + 4 * c;
    uint2 a5[10], a3[10];
    const uint32_t aa = tb + T_5 + 4 * (8 + 2 * g - 2 * c);
#pragma unroll
    for (int m = 0; m < 10; m++) { a5[m] = lds64(aa + 32 * m); a3[m] = lds64(aa + 384 + 32 * m); }
    float T[6][4];
#pragma unroll
    for (int i = 0; i < 6; i++) T[i][0] = T[i][1] = T[i][2] = T[i][3] = 0.f;
    uint32_t x5[2] = {0, 0}, x3[2] = {0, 0}, yb[4], lq[4];
    uint32_t lqa = qa, sta = st + 256 * 8;
    uint2 sv;
    auto fetch = [&]() {
      yb[0] = lds32(y0a); yb[1] = lds32(y1a); yb[2] = lds32(y0a + 64); yb[3] = lds32(y1a + 64);
      ldsm4(lq, lqa);
      sv = lds64(min(sta, st + 256 * 15));
      y0a += 128; y1a += 128; lqa += 128; sta += 256;
    };
    fetch();
#pragma unroll 2
    for (int kap = -1; kap < 13; kap++) {
      float yn[2][4];
      mma0(yn[0][0], yn[0][1], yn[0][2], yn[0][3], bx0, bx1, bx2, bx3, yb[0], yb[1]);
      mma0(yn[1][0], yn[1][1], yn[1][2], yn[1][3], bx0, bx1, bx2, bx3, yb[2], yb[3]);
      sts64_p(kap > 0, sta - 256 * 7, pack_bf(T[0][0], T[0][1]), pack_bf(T[0][2], T[0][3]));
#pragma unroll
      for (int i = 0; i < 5; i++)
        mmac_p((unsigned)kap < 12u - i, T[i], a5[2 * i + 1].x, a5[2 * i + 1].y, a5[2 * i].x, a5[2 * i].y, x5[0], x5[1], T[i + 1]);
      const float ci[4] = {bf_lo(sv.x), bf_hi(sv.x), bf_lo(sv.y), bf_hi(sv.y)};
      mmac_p(kap < 7, T[5], lq[0], lq[1], lq[2], lq[3], lb0, lb1, ci);
      fetch();
#pragma unroll
      for (int i = 0; i < 5; i++)
        mma_p((unsigned)kap < 12u - i, T[i], a3[2 * i + 1].x, a3[2 * i + 1].y, a3[2 * i].x, a3[2 * i].y, x3[0], x3[1]);
#pragma unroll
      for (int hh = 0; hh < 2; hh++) { x5[hh] = pack_bf(yn[hh][0], yn[hh][1]); x3[hh] = pack_bf(yn[hh][2], yn[hh][3]); }
    }
  }
  TS(45);
  {
    uint32_t F[66];
    const uint32_t fa = tb + T_D + 32 + 4 * x;
#pragma unroll
    for (int m = 0; m < 66; m++) F[m] = lds32(fa + 32 * m);
    float T[5][4];
#pragma unroll
    for (int i = 0; i < 5; i++) T[i][0] = T[i][1] = T[i][2] = T[i][3] = 0.f;
    uint32_t qd[8][4], held[2] = {0, 0};
    uint32_t qp = qa + 128 * 15, sta = st + 256 * 14;
    uint4* yd = ydst + 19 * 16;
#pragma unroll
    for (int i = 0; i < 6; i++) ldsm4(qd[i], qp - 16 * i);
    uint2 sv = lds64(sta + 256);
    float ci[4] = {bf_lo(sv.x), bf_hi(sv.x), bf_lo(sv.y), bf_hi(sv.y)};
    mbar_wait(BAR(MB_ZOK));
    TS(46);
#pragma unroll 2
    for (int be = 15; be >= 0; be--) {
#pragma unroll
      for (int k = 4; k >= 1; k--)
        mmac_p(be <= 15 - k, T[k], qd[0][0], qd[0][1], qd[0][2], qd[0][3], F[16 * k + 1], F[16 * k], T[k - 1]);
      mmac(T[0], qd[0][0], qd[0][1], qd[0][2], qd[0][3], F[1], F[0], ci);
      ldsm4(qd[6], qp - 16 * 6);
      ldsm4(qd[7], qp - 16 * 7);
      sv = lds64(sta);
#pragma unroll
      for (int i = 1; i < 8; i++) {
#pragma unroll
        for (int k = 3; k >= 0; k--)
          mma_p(k == 0 || be <= 15 - k, T[k], qd[i][0], qd[i][1], qd[i][2], qd[i][3], F[16 * k + 2 * i + 1], F[16 * k + 2 * i]);
        if (i < 7) ldsm4(qd[i - 1], qp - 128 - 16 * (i - 1));
        if (i == 2) {
          const uint32_t w0 = pack_bf(T[4][0], T[4][1]), w1 = pack_bf(T[4][2], T[4][3]);
          st_x_p(be <= 10 && !(be & 1), yd, nz(w0), w1, held[0], held[1]);
          held[0] = w0; held[1] = w1;
        }
        if (i == 4) {
          if (be <= 4) sv = make_uint2(0, 0);
          ci[0] = bf_lo(sv.x); ci[1] = bf_hi(sv.x); ci[2] = bf_lo(sv.y); ci[3] = bf_hi(sv.y);
        }
      }
      qp -= 128; sta -= 256; yd -= 16;
    }
#pragma unroll
    for (int B = 1; B >= 0; B--)
      st_x(ydst + B * 32, nz(pack_bf(T[2 * B][0], T[2 * B][1])), pack_bf(T[2 * B][2], T[2 * B][3]),
           pack_bf(T[2 * B + 1][0], T[2 * B + 1][1]), pack_bf(T[2 * B + 1][2], T[2 * B + 1][3]));
  }
}

__device__ __forceinline__ void feat(const float (&acc)[48], int j0, const uint32_t (&wf)[4], uint32_t* w) {
  const uint32_t a0 = pack_bf(acc[4 * j0], acc[4 * j0 + 1]), a1 = pack_bf(acc[4 * j0 + 2], acc[4 * j0 + 3]);
  const uint32_t a2 = pack_bf(acc[4 * j0 + 4], acc[4 * j0 + 5]), a3 = pack_bf(acc[4 * j0 + 6], acc[4 * j0 + 7]);
  float p[8];
  mma0(p[0], p[1], p[2], p[3], a0, a1, a2, a3, wf[0], wf[1]);
  mma0(p[4], p[5], p[6], p[7], a0, a1, a2, a3, wf[2], wf[3]);
  w[0] = pack_bf(p[0], p[2]); w[1] = pack_bf(p[1], p[3]); w[2] = pack_bf(p[4], p[6]); w[3] = pack_bf(p[5], p[7]);
}
__device__ __forceinline__ void dual_softmax(const uint32_t* w, uint32_t* e) {
  const float L = 1.44268798828125f;
  uint32_t mx = bmax2(bmax2(w[0], w[1]), bmax2(w[2], w[3]));
  uint32_t mn = bmin2(bmin2(w[0], w[1]), bmin2(w[2], w[3]));
  mx = bmax2(mx, __shfl_xor_sync(0xffffffffu, mx, 1));
  mn = bmin2(mn, __shfl_xor_sync(0xffffffffu, mn, 1));
  mx = bmax2(mx, __shfl_xor_sync(0xffffffffu, mx, 2));
  mn = bmin2(mn, __shfl_xor_sync(0xffffffffu, mn, 2));
  const float mx0 = bf_lo(mx) * -L, mx1 = bf_hi(mx) * -L, mn0 = bf_lo(mn) * L, mn1 = bf_hi(mn) * L;
  float ep[2][4], em[2][4];
#pragma unroll
  for (int i = 0; i < 4; i++) {
    const float x0 = bf_lo(w[i]), x1 = bf_hi(w[i]);
    ep[0][i] = ex2(fmaf(x0, L, mx0)); em[0][i] = ex2(fmaf(x0, -L, mn0));
    ep[1][i] = ex2(fmaf(x1, L, mx1)); em[1][i] = ex2(fmaf(x1, -L, mn1));
  }
  __half2 sp = __floats2half2_rn((ep[0][0] + ep[0][1]) + (ep[0][2] + ep[0][3]), (ep[1][0] + ep[1][1]) + (ep[1][2] + ep[1][3]));
  __half2 sm = __floats2half2_rn((em[0][0] + em[0][1]) + (em[0][2] + em[0][3]), (em[1][0] + em[1][1]) + (em[1][2] + em[1][3]));
  sp = __hadd2(sp, __shfl_xor_sync(0xffffffffu, sp, 1));
  sm = __hadd2(sm, __shfl_xor_sync(0xffffffffu, sm, 1));
  sp = __hadd2(sp, __shfl_xor_sync(0xffffffffu, sp, 2));
  sm = __hadd2(sm, __shfl_xor_sync(0xffffffffu, sm, 2));
  const float rp[2] = {rcp(__low2float(sp)), rcp(__high2float(sp))}, rm[2] = {rcp(__low2float(sm)), rcp(__high2float(sm))};
#pragma unroll
  for (int i = 0; i < 4; i++) {
    const int r = i & 1, k = i & 2;
    e[i] = pack_bf(ep[r][k] * rp[r], ep[r][k + 1] * rp[r]);
    e[4 + i] = pack_bf(em[r][k] * rm[r], em[r][k + 1] * rm[r]);
  }
}

__global__ void __launch_bounds__(NTHREADS, 1)
fused_kernel(const Params P, const __grid_constant__ CUtensorMap mx, const __grid_constant__ CUtensorMap mw,
             const __grid_constant__ CUtensorMap mo, const __grid_constant__ CUtensorMap mu,
             const __grid_constant__ CUtensorMap mout) {
  asm volatile("prefetch.tensormap [%0];" ::"l"(&mw) : "memory");
  asm volatile("prefetch.tensormap [%0];" ::"l"(&mx) : "memory");
  asm volatile("prefetch.tensormap [%0];" ::"l"(&mu) : "memory");
  constexpr uint32_t sb = SB;
  const int tid = threadIdx.x, lane = tid & 31;
  const int warp = __shfl_sync(0xffffffffu, tid >> 5, 0);
  const int b = blockIdx.x, oct = b >> 3, i8 = b & 7;
  const int rt = oct < 8 ? oct : 15 - oct;
  const int hp = (oct >> 3) * 8 + i8;

  const int d = b * 4 + ((tid >> 5) & 3);
  KgenRaw raw = {}, raw3 = {};
  unsigned short dsk = 0;
  if (tid < 384) {
    raw = kgen_load(P, d, tid >> 7, lane);
    raw3 = kgen_load(P, d, 3, lane);
    dsk = __ldg((const unsigned short*)P.Dskip + d);
  }
  if (warp >= 12) asm volatile("setmaxnreg.dec.sync.aligned.u32 32;");
  if (warp == 12) {
    if (lane == 0) {
#pragma unroll
      for (int i = 0; i < 9; i++) mbar_init(BAR(i), 1);
      asm volatile("fence.mbarrier_init.release.cluster;" ::: "memory");
    }
    __syncwarp();
    if (lane < 9) mbar_expect(BAR(0) + 8 * lane, lane == 0 ? 16384 : (lane < 8 ? 28672 : 29696));
    __syncwarp();
    nb_arrive(NB_PREP, 448);
    nb_arrive(NB_RDY, 128);
#pragma unroll 1
    for (int kb = 0; kb < 8; kb++) {
      if (kb == STEP_U) e_tma5d(sb + OFF_STG0, &mu, BAR(MB_URAW), i8 * 64, oct * 4);
      e_tma3d(sb + OFF_W + kb * 12288, &mw, BAR(MB_FULL) + 8 * kb, hp * 32, kb * 64, 0);
      if (kb < 5) e_tma2d(sb + OFF_X + (kb < 2 ? kb + 3 : kb - 2) * 16384, &mx, BAR(MB_FULL) + 8 * kb, kb * 64, rt * 256);
    }
    if (smem_u32(smem_raw) != SB) __trap();
  }
  if (warp >= 12) {
    if (warp == 12) {
      nb_sync(NB_PROD, 64);
      e_prefetch(P.x + (size_t)(rt * 256 + hp * 16) * 512, 16384);
      e_bulk(sb + OFF_PHI, P.wphi + hp * 512, 1024, BAR(MB_FULL + 7));
      uint32_t slot = sb + OFF_X + 3 * 16384;
#pragma unroll 1
      for (int n = 0; n < 11; n++) {
        mbar_wait(BAR(MB_EMPTY) + 8 * n);
        const int m = n + 5;
        e_tma2d(slot, &mx, BAR(MB_FULL) + 8 * m, (m & 7) * 64, rt * 256 + (m >> 3) * 128);
        slot = slot == sb + OFF_X + 4 * 16384 ? sb + OFF_X : slot + 16384;
        if (n == 7) e_prefetch(P.wo + (size_t)b * 2048, 4096);
      }
#pragma unroll 1
      for (int i = 0; i < 8; i++) {
        mbar_wait(BAR(MB_EMPTY + 10) + 8 * ((0x54332100u >> (4 * i)) & 7));
        const int w0 = (0x54736210u >> (4 * i)) & 7;
        const int col = (hp & 3) * 128 + (w0 >> 2) * 64;
        e_tma2d(sb + OFF_W + w0 * 16384, &mo, BAR(MB_WO) + 8 * (w0 >> 2), col, w0 * 64);
        e_tma2d(sb + OFF_W + w0 * 16384 + 8192, &mo, BAR(MB_WO) + 8 * (w0 >> 2), col ^ 64, w0 * 64);
      }
    } else {
      if (warp == 13) {
        if (lane == 0) {
#pragma unroll
          for (int i = 9; i < 38; i++) mbar_init(BAR(i), i < MB_EMPTY ? 1 : (i < MB_CLOSE ? 4 : 11));
          asm volatile("fence.mbarrier_init.release.cluster;" ::: "memory");
        }
        __syncwarp();
        if (lane < 10) mbar_expect(BAR(MB_FULL + 8) + 8 * lane, lane < 8 ? 16384 : 65536);
        __syncwarp();
        nb_arrive(NB_PROD, 64);
        nb_arrive(NB_PREP, 448);
      }
      nb_sync(NB_RDY, 128);
      const unsigned cnt0 = ld_x32(g_cnt + 256);
      mbar_wait(BAR(MB_URAW));
      if (tid == 416) TS1(48);
      uint4* dst = g_uT + (size_t)(i8 * 64 + (lane >> 2)) * 256 + (lane & 1) * 128 + oct * 8 + ((lane >> 1) & 1);
#pragma unroll 1
      for (int i = warp - 13; i < 32; i += 3) {
        uint32_t r[4];
        ldsm4t(r, sb + OFF_STG0 + (i >> 3) * 4096 + lane * 128 + (((i ^ lane) & 7) << 4));
        dst[(i & 7) * 2048 + (i >> 3) * 2] = make_uint4(r[0], r[1], r[2], r[3]);
      }
      if (lane == 0) mbar_arrive(BAR(MB_CLOSE));
      nb_sync(NB_INIT, 96);
      if (warp > 13) {
        mbar_wait(BAR(MB_EMPTY + ZERO_STEP));
        uint4* po = g_o + (size_t)(rt * 4 * 32 + hp * 2) * 128;
        uint4* py = g_y + (size_t)b * 1024;
        uint4* pp = g_part + (size_t)(hp * 8 + rt) * 144;
#pragma unroll 1
        for (int i = tid - 448; i < ZERO_N; i += 64) {
          st_x(po + (i >> 8) * 4096 + (i & 255), 0, 0, 0, 0);
          st_x(py + i, 0, 0, 0, 0);
          if (i < 144) st_x(pp + i, 0, 0, 0, 0);
        }
        nb_sync(NB_ZERO, 64);
        if (warp == 15) return;
      }
      if (lane == 0) TS1(warp == 13 ? 49 : 55);
      if (lane == 0)
        asm volatile("red.release.gpu.global.add.u32 [%0], %1;" ::"l"(g_cnt + (warp == 13 ? i8 : 8) * 32), "r"(warp == 13 ? 8 : 1) : "memory");
      if (lane == 0) TS1(warp == 13 ? 50 : 56);
#pragma unroll 1
      for (int i = 0; i < SPIN_MAX; i++) {
        unsigned v;
        asm volatile("ld.acquire.gpu.global.u32 %0, [%1];" : "=r"(v) : "l"(g_cnt + (warp == 13 ? b >> 4 : 8) * 32) : "memory");
        if ((int)(v - ((cnt0 & ~(unsigned)(NCTA - 1)) + NCTA)) >= 0) break;
      }
      if (lane == 0) TS1(warp == 13 ? 51 : 57);
      if (warp == 14) {
        if (lane == 0) mbar_arrive(BAR(MB_ZOK));
      } else {
        mbar_wait(BAR(MB_EMPTY + 11));
        sts128(sb + OFF_U + (lane >> 4) * U_CH + ((lane >> 3) & 1) * U_ODD + (lane & 7) * 16, 0, 0, 0, 0);
        sts128(sb + OFF_U + (2 + (lane >> 4)) * U_CH + ((lane >> 3) & 1) * U_ODD + (lane & 7) * 16, 0, 0, 0, 0);
        asm volatile("fence.proxy.async.global;" ::: "memory");
        __syncwarp();
        e_expect(BAR(MB_UFULL), 16384);
#pragma unroll 1
        for (int i = 0; i < 8; i++)
          e_bulk(sb + OFF_U + (i >> 1) * U_CH + (i & 1) * U_ODD + U_PAD, g_uT + (size_t)(b * 8 + i) * 128, 2048, BAR(MB_UFULL));
      }
    }
    return;
  }

  asm volatile("setmaxnreg.inc.sync.aligned.u32 160;");
  const int wg = warp >> 2, w = warp & 3, t = tid & 127;
  const int g = lane >> 2, c = lane & 3;
  const uint32_t tb = sb + OFF_T + w * T_CH;
  {
    float k[5][4], k2048 = 0.f, dt;
#pragma unroll
    for (int j = 0; j < 5; j++) k[j][0] = k[j][1] = k[j][2] = k[j][3] = 0.f;
    const uint32_t kp = tb + (wg & 1) * 2608;
#pragma unroll 1
    for (int r = 0; r <= (wg >> 1); r++) {
      kgen_unit(raw, lane, wg == 2 ? sb + OFF_STG0 + 16384 + w * 2048 : (kp + 127) & ~127u, r ? BAR(MB_EMPTY + 7) : 0u, dt, k, k2048);
      raw = raw3;
      TS(40 + wg + r);
      if (r == 0) {
        if (wg != 2) {
#pragma unroll
          for (int j = 0; j < 5; j++) sts128(kp + j * 512 + lane * 16, fu(k[j][0]), fu(k[j][1]), fu(k[j][2]), fu(k[j][3]));
          k2048 += __shfl_xor_sync(0xffffffffu, k2048, 16);
          k2048 += __shfl_xor_sync(0xffffffffu, k2048, 8);
          if (lane < 8) sts32(kp + 2560 + lane * 4, fu(k2048));
        } else if ((fu(k[0][0]) & fu(k[1][0]) & fu(k[2][0]) & fu(k[3][0]) & fu(k[4][0])) == 0xffffffffu) {
          sts32(kp, 0);
        }
        nb_sync(NB_PREP, 448);
        if (wg == 2) {
#pragma unroll 1
          for (int q = 0; q < 2; q++) {
            const uint32_t src = tb + q * 2608;
#pragma unroll
            for (int j = 0; j < 5; j++) {
              const uint4 v = lds128(src + j * 512 + lane * 16);
              k[j][0] += uf(v.x); k[j][1] += uf(v.y); k[j][2] += uf(v.z); k[j][3] += uf(v.w);
            }
            if (lane < 8) k2048 += uf(lds32(src + 2560 + lane * 4));
          }
        }
      }
    }
    if (wg == 2) {
      if (lane == 0 && (fu(k[0][0]) & fu(k[1][0]) & fu(k[2][0]) & fu(k[3][0]) & fu(k[4][0])) != 0xffffffffu)
        mbar_arrive(BAR(MB_CLOSE));
      TS(34);
#pragma unroll
      for (int o2 = 16; o2; o2 >>= 1) k2048 += __shfl_xor_sync(0xffffffffu, k2048, o2);
      const float sc = 2.f * dt;
#pragma unroll
      for (int j = 0; j < 5; j++) { k[j][0] *= sc; k[j][1] *= sc; k[j][2] *= sc; k[j][3] *= sc; }
      k2048 *= sc;
      if (lane == 0) k[0][0] += bf_lo(dsk);
      build_tables(tb, lane, k, k2048);
      TS(35);
      mbar_wait(BAR(MB_UFULL));
      conv_channel(sb + OFF_U + w * U_CH, tb, lane, g_y + (size_t)d * 256 + lane);
      nb_arrive(NB_BDONE, 384);
      TS(37);
      const int lam = w * 8 + g;
      const uint4* src = g_y + (size_t)(oct * 32 + c * 8) * 256 + i8 * 32 + lam;
      uint4 v[8];
#pragma unroll 1
      for (int it = 0; it < SPIN_MAX; it++) {
        uint32_t m = 0xffffffffu;
#pragma unroll
        for (int i = 0; i < 8; i++) v[i] = ld_x(src + i * 256);
#pragma unroll
        for (int i = 0; i < 8; i++) m = min(m, v[i].x);
        if (__all_sync(0xffffffffu, m != 0)) break;
      }
      __nv_bfloat16* dst = P.out + (size_t)(i8 * 256 + (lam >> 2) * 16 + (lam & 3) * 2) * 1024 + 512 + oct * 32 + c * 8;
#pragma unroll
      for (int i = 0; i < 8; i++) *(uint4*)(dst + (size_t)((i >> 2) * 128 + ((i >> 1) & 1) * 8 + (i & 1)) * 1024) = tr_row(v, i);
      TS(38);
      GT(63);
      return;
    }
    if (wg == 1) mbar_wait(BAR(MB_CLOSE));
    TS(wg * 16 + 1);
  }

  float acc[2][48];
  {
    uint32_t fb = BAR(MB_FULL) + 64 * wg;
    uint32_t da = (uint32_t)mkdesc(sb + OFF_X, 16, 0, 0) + (wg ? 1024 : 3072), db = (uint32_t)mkdesc(sb + OFF_W, 4096, 0, 0);
    constexpr uint64_t ha = mkdesc(0, 0, 1024, 1), hb = mkdesc(0, 0, 512, 2);
#pragma unroll 1
    for (int kb = 0; kb < 8; kb++) {
      mbar_wait(fb);
      if (kb == 0) TS(wg * 16 + 2);
      WG_FENCE();
#pragma unroll
      for (int k = 0; k < 4; k++) {
        wgmma_ss_n96(acc[0], ha | (da + 2 * k), hb | (db + 64 * k), k ? 1 : kb);
        wgmma_ss_n96(acc[1], ha | (da + 2 * k + 512), hb | (db + 64 * k), k ? 1 : kb);
      }
      WG_COMMIT();
      WG_WAIT(1);
      if (kb > 0 && lane == 0) mbar_arrive(fb + 8 * (MB_EMPTY - MB_FULL - 1));
      fb += 8; db += 768;
      da = da == (uint32_t)mkdesc(sb + OFF_X + 65536, 16, 0, 0) ? da - 4096 : da + 1024;
    }
    WG_WAIT(0);
    if (lane == 0) mbar_arrive(fb + 8 * (MB_EMPTY - MB_FULL - 1));
    mbar_wait(fb + 8 * (MB_EMPTY - MB_FULL - 1));
  }
  uint32_t wf[2][4];
  ldsm4t(wf[0], sb + OFF_PHI + (lane & 15) * 32 + (lane >> 4) * 16);
  ldsm4t(wf[1], sb + OFF_PHI + 512 + (lane & 15) * 32 + (lane >> 4) * 16);
  TS(wg * 16 + 3);

  uint32_t pw[32], eq[32];
#pragma unroll
  for (int u = 0; u < 4; u++)
#pragma unroll
    for (int h = 0; h < 2; h++) feat(acc[u & 1], (u < 2 ? 4 : 0) + 2 * h, wf[h], pw + 8 * u + 4 * h);
  {
    uint32_t all = 0xffffffffu;
#pragma unroll
    for (int i = 0; i < 16; i++) all &= pw[2 * i];
    if (wg == 0 && lane == 0 && all != 0xffffffffu) mbar_arrive(BAR(MB_CLOSE));
  }
  mbar_wait(BAR(MB_CLOSE));
  const uint32_t stg0 = sb + OFF_STG0, stg1 = sb + OFF_X + 32768;
  uint32_t sl = (wg ? stg1 : stg0) + w * 3072 + lane * 16;
#pragma unroll
  for (int mt = 0; mt < 2; mt++)
#pragma unroll
    for (int h = 0; h < 2; h++) {
      const float* a = acc[mt] + 32 + 8 * h;
      stsm4(sl + mt * 12288 + 2048 + h * 512, pack_bf(a[0], a[1]), pack_bf(a[2], a[3]), pack_bf(a[4], a[5]), pack_bf(a[6], a[7]));
    }
#pragma unroll 1
  for (int u = 0; u < 4; u++) {
#pragma unroll
    for (int i = 0; i < 16; i++) eq[i] = eq[16 + i];
    dual_softmax(pw, eq + 16);
    dual_softmax(pw + 4, eq + 24);
    if (u < 2) {
#pragma unroll
      for (int i = 0; i < 4; i++) stsm4(sl + i * 512, eq[16 + 4 * i], eq[17 + 4 * i], eq[18 + 4 * i], eq[19 + 4 * i]);
      if (wg) nb_arrive(NB_ST0 + u, 256);
      sl += 12288;
    }
#pragma unroll
    for (int i = 0; i < 24; i++) pw[i] = pw[i + 8];
  }
  TS(wg * 16 + 4);
  const uint32_t kvs = stg0;
  if (wg == 0) {
    nb_sync(NB_WG0, 128);
    mbar_wait(BAR(MB_ZOK));
    mbar_wait(BAR(MB_EMPTY + 15));
    float kv[12];
#pragma unroll
    for (int i = 0; i < 12; i++) kv[i] = 0.f;
    const int mi = lane >> 3;
    const uint32_t ao = w * 512 + (lane & 7) * 16 + ((mi & 1) * 2 + (mi >> 1)) * 128, bo = 2048 + (w >> 1) * 512 + lane * 16;
#pragma unroll 1
    for (int j = 0; j < 4; j++) {
      if (j >= 2) nb_sync(NB_ST0 + j - 2, 256);
      const uint32_t sg = (j >= 2 ? stg1 : stg0) + (j & 1) * 12288;
      uint32_t a[4][4], bb[4][4];
#pragma unroll
      for (int s = 0; s < 4; s++) { ldsm4t(a[s], sg + s * 3072 + ao); ldsm4t(bb[s], sg + s * 3072 + bo); }
#pragma unroll
      for (int s = 0; s < 4; s++) {
        mma(kv[0], kv[1], kv[2], kv[3], a[s][0], a[s][1], a[s][2], a[s][3], bb[s][0], bb[s][1]);
        mma(kv[4], kv[5], kv[6], kv[7], a[s][0], a[s][1], a[s][2], a[s][3], bb[s][2], bb[s][3]);
        mma(kv[8], kv[9], kv[10], kv[11], a[s][0], a[s][1], a[s][2], a[s][3], 0x3F803F80u, 0x3F803F80u);
      }
    }
    uint4* pp = g_part + (size_t)(hp * 8 + rt) * 144;
    st_x(pp + t, nz(pack_bf(kv[0], kv[1])), pack_bf(kv[2], kv[3]), pack_bf(kv[4], kv[5]), pack_bf(kv[6], kv[7]));
    if (c < 2) st_x32((uint32_t*)(pp + 128) + w * 16 + c * 8 + g, nz(fu(c ? kv[10] : kv[8])));
    TS(5);
    const uint4* ps = g_part + (size_t)hp * 8 * 144 + t;
    const uint32_t* zs = (const uint32_t*)(g_part + (size_t)(hp * 8 + (lane >> 4) * 4) * 144 + 128) + w * 16 + (lane & 15);
    uint4 v[8];
    uint32_t zv[4];
#pragma unroll 1
    for (int it = 0; it < SPIN_MAX; it++) {
#pragma unroll
      for (int i = 0; i < 8; i++) v[i] = ld_x(ps + i * 144);
#pragma unroll
      for (int i = 0; i < 4; i++) zv[i] = ld_x32(zs + i * 576);
      uint32_t m = min(min(zv[0], zv[1]), min(zv[2], zv[3]));
#pragma unroll
      for (int i = 0; i < 8; i++) m = min(m, v[i].x);
      if (__all_sync(0xffffffffu, m != 0)) break;
    }
    float s4[4][4];
#pragma unroll
    for (int i = 0; i < 4; i++) s4[i][0] = s4[i][1] = s4[i][2] = s4[i][3] = 0.f;
    const uint32_t eye = (g >> 1) == c ? ((g & 1) ? 0x3F800000u : 0x3F80u) : 0u;
#pragma unroll
    for (int r = 0; r < 8; r++) {
      mma_k8(s4[(r & 1) * 2], v[r].x, v[r].y, eye);
      mma_k8(s4[(r & 1) * 2 + 1], v[r].z, v[r].w, eye);
    }
    float s[8];
#pragma unroll
    for (int i = 0; i < 8; i++) s[i] = s4[i >> 2][i & 3] + s4[2 + (i >> 2)][i & 3];
    float zsum = (uf(zv[0]) + uf(zv[1])) + (uf(zv[2]) + uf(zv[3]));
    zsum += __shfl_xor_sync(0xffffffffu, zsum, 16);
    stsm4(kvs + w * 512 + lane * 16, pack_bf(s[0], s[1]), pack_bf(s[2], s[3]), pack_bf(s[4], s[5]), pack_bf(s[6], s[7]));
    if (lane < 16) sts16(kvs + 2048 + (w * 16 + lane) * 2, pack_bf(zsum, 0.f));
    TS(6);
  }
  nb_sync(NB_KV, 256);
  {
    uint32_t kb_[4][4], zb[8];
#pragma unroll
    for (int i = 0; i < 4; i++) ldsm4t(kb_[i], kvs + i * 512 + lane * 16);
#pragma unroll
    for (int i = 0; i < 8; i++) zb[i] = lds32(kvs + 2048 + i * 16 + c * 4);
    uint4* od = g_o + (size_t)((rt * 4 + wg * 2) * 32 + hp * 2) * 128 + t;
#pragma unroll 1
    for (int mt = 0; mt < 2; mt++) {
#pragma unroll
      for (int h = 0; h < 2; h++) {
        const uint32_t* e = eq + 8 * h;
        float n[8], dn[4];
        mma0(dn[0], dn[1], dn[2], dn[3], e[0], e[1], e[2], e[3], zb[4 * h], zb[4 * h + 1]);
        mma0(n[0], n[1], n[2], n[3], e[0], e[1], e[2], e[3], kb_[2 * h][0], kb_[2 * h][1]);
        mma0(n[4], n[5], n[6], n[7], e[0], e[1], e[2], e[3], kb_[2 * h][2], kb_[2 * h][3]);
        mma(dn[0], dn[1], dn[2], dn[3], e[4], e[5], e[6], e[7], zb[4 * h + 2], zb[4 * h + 3]);
        mma(n[0], n[1], n[2], n[3], e[4], e[5], e[6], e[7], kb_[2 * h + 1][0], kb_[2 * h + 1][1]);
        mma(n[4], n[5], n[6], n[7], e[4], e[5], e[6], e[7], kb_[2 * h + 1][2], kb_[2 * h + 1][3]);
        const float r0 = rcp(dn[0] + 1e-6f), r1 = rcp(dn[2] + 1e-6f);
        st_x(od + h * 128, nz(pack_bf(n[0] * r0, n[1] * r0)), pack_bf(n[2] * r1, n[3] * r1), pack_bf(n[4] * r0, n[5] * r0),
             pack_bf(n[6] * r1, n[7] * r1));
      }
#pragma unroll
      for (int i = 0; i < 16; i++) eq[i] = eq[16 + i];
      od += 4096;
    }
  }
  TS(wg * 16 + 7);
  const int rb = rt * 4 + (hp >> 2);
  const uint4* osrc = g_o + (size_t)(rb * 32 + wg * 16) * 128 + t;
  uint4 af[16];
  {
    const uint32_t* probe = (const uint32_t*)(osrc - lane + (lane & 15) * 128 + (lane >> 4) * 31);
#pragma unroll 1
    for (int it = 0; it < SPIN_MAX; it++) {
      uint32_t m = ld_x32(probe);
#pragma unroll
      for (int i = 0; i < 4; i++) af[i] = ld_x(osrc + i * 128);
#pragma unroll
      for (int i = 0; i < 4; i++) m = min(m, af[i].x);
      if (__all_sync(0xffffffffu, m != 0)) break;
    }
  }
#pragma unroll
  for (int i = 4; i < 16; i++) af[i] = ld_x(osrc + i * 128);
  TS(wg * 16 + 8);
  mbar_wait(BAR(MB_WO) + 8 * wg);
  nb_sync(NB_BDONE, 384);
  TS(wg * 16 + 9);
  float oc[64];
  {
    const uint64_t db = mkdesc(sb + OFF_W, 8192, 1024, 1) + wg * 4096;
#pragma unroll
    for (int j = 0; j < 4; j++) {
      if (j) {
#pragma unroll 1
        for (int it = 0; it < SPIN_MAX; it++) {
          const uint32_t m = min(min(af[4 * j].x, af[4 * j + 1].x), min(af[4 * j + 2].x, af[4 * j + 3].x));
          if (__all_sync(0xffffffffu, m != 0)) break;
#pragma unroll
          for (int i = 0; i < 4; i++) af[4 * j + i] = ld_x(osrc + (4 * j + i) * 128);
        }
      }
      WG_FENCE();
#pragma unroll
      for (int k = 0; k < 4; k++) wgmma_rs_n128(oc, af[4 * j + k], db + 128 * k + 1024 * j, j | k);
    }
    WG_COMMIT();
    WG_WAIT(0);
  }
  TS(wg * 16 + 10);
  const uint32_t xo = stg1 + wg * 16384 + t * 16, xi = stg1 + (wg ^ 1) * 16384 + t * 16;
#pragma unroll
  for (int i = 0; i < 8; i++) sts128(xo + i * 2048, fu(oc[32 + 4 * i]), fu(oc[33 + 4 * i]), fu(oc[34 + 4 * i]), fu(oc[35 + 4 * i]));
  nb_sync(NB_RED, 256);
  const uint32_t ot = stg0 + warp * 2048;
#pragma unroll
  for (int i = 0; i < 8; i += 2) {
    const uint4 v0 = lds128(xi + i * 2048), v1 = lds128(xi + i * 2048 + 2048);
    stsm4(ot + (lane & 15) * 128 + (((i + (lane >> 4)) ^ (lane & 7)) << 4),
          pack_bf(oc[4 * i] + uf(v0.x), oc[4 * i + 1] + uf(v0.y)), pack_bf(oc[4 * i + 2] + uf(v0.z), oc[4 * i + 3] + uf(v0.w)),
          pack_bf(oc[4 * i + 4] + uf(v1.x), oc[4 * i + 5] + uf(v1.y)), pack_bf(oc[4 * i + 6] + uf(v1.z), oc[4 * i + 7] + uf(v1.w)));
  }
  asm volatile("fence.proxy.async.shared::cta;" ::: "memory");
  __syncwarp();
  e_store2d(&mout, ot, (hp & 3) * 128 + wg * 64, rb * 64 + w * 16);
  TS(wg * 16 + 11);
  GT(61 + wg);
}

typedef CUresult (*EncodeFn)(CUtensorMap*, CUtensorMapDataType, cuuint32_t, void*, const cuuint64_t*, const cuuint64_t*,
                             const cuuint32_t*, const cuuint32_t*, CUtensorMapInterleave, CUtensorMapSwizzle,
                             CUtensorMapL2promotion, CUtensorMapFloatOOBfill);

}

extern "C" void kernel_launch(void* const* d_in, const int* in_sizes, int n_in, void* d_out, int out_size) {
  (void)in_sizes; (void)n_in; (void)out_size;
  void* fn = nullptr;
  cudaDriverEntryPointQueryResult qr;
  cudaGetDriverEntryPoint("cuTensorMapEncodeTiled", &fn, cudaEnableDefault, &qr);
  EncodeFn enc = (EncodeFn)fn;
  CUtensorMap mx, mw, mo, mu, mout;
  const cuuint32_t es[5] = {1, 1, 1, 1, 1};
  {
    cuuint64_t dims[2] = {512, 2048}, st[1] = {1024};
    cuuint32_t box[2] = {64, 128};
    enc(&mx, CU_TENSOR_MAP_DATA_TYPE_BFLOAT16, 2, d_in[0], dims, st, box, es, CU_TENSOR_MAP_INTERLEAVE_NONE,
        CU_TENSOR_MAP_SWIZZLE_128B, CU_TENSOR_MAP_L2_PROMOTION_L2_128B, CU_TENSOR_MAP_FLOAT_OOB_FILL_NONE);
  }
  {
    cuuint64_t dims[3] = {512, 512, 3}, st[2] = {3072, 1024};
    cuuint32_t box[3] = {32, 64, 3};
    enc(&mw, CU_TENSOR_MAP_DATA_TYPE_BFLOAT16, 3, d_in[1], dims, st, box, es, CU_TENSOR_MAP_INTERLEAVE_NONE,
        CU_TENSOR_MAP_SWIZZLE_64B, CU_TENSOR_MAP_L2_PROMOTION_L2_128B, CU_TENSOR_MAP_FLOAT_OOB_FILL_NONE);
  }
  {
    cuuint64_t dims[2] = {512, 512}, st[1] = {1024};
    cuuint32_t box[2] = {64, 64};
    enc(&mo, CU_TENSOR_MAP_DATA_TYPE_BFLOAT16, 2, d_in[3], dims, st, box, es, CU_TENSOR_MAP_INTERLEAVE_NONE,
        CU_TENSOR_MAP_SWIZZLE_128B, CU_TENSOR_MAP_L2_PROMOTION_L2_128B, CU_TENSOR_MAP_FLOAT_OOB_FILL_NONE);
  }
  {
    cuuint64_t dims[5] = {512, 2, 4, 4, 64}, st[4] = {1024, 8192, 2048, 32768};
    cuuint32_t box[5] = {64, 2, 4, 4, 4};
    enc(&mu, CU_TENSOR_MAP_DATA_TYPE_BFLOAT16, 5, d_in[4], dims, st, box, es, CU_TENSOR_MAP_INTERLEAVE_NONE,
        CU_TENSOR_MAP_SWIZZLE_128B, CU_TENSOR_MAP_L2_PROMOTION_L2_128B, CU_TENSOR_MAP_FLOAT_OOB_FILL_NONE);
  }
  {
    cuuint64_t dims[2] = {1024, 2048}, st[1] = {2048};
    cuuint32_t box[2] = {64, 16};
    enc(&mout, CU_TENSOR_MAP_DATA_TYPE_BFLOAT16, 2, d_out, dims, st, box, es, CU_TENSOR_MAP_INTERLEAVE_NONE,
        CU_TENSOR_MAP_SWIZZLE_128B, CU_TENSOR_MAP_L2_PROMOTION_NONE, CU_TENSOR_MAP_FLOAT_OOB_FILL_NONE);
  }
  Params P;
  P.x = (const __nv_bfloat16*)d_in[0];
  P.wphi = (const __nv_bfloat16*)d_in[2];
  P.wo = (const __nv_bfloat16*)d_in[3];
  P.u = (const __nv_bfloat16*)d_in[4];
  P.logA = (const __nv_bfloat16*)d_in[5];
  P.Aim = (const __nv_bfloat16*)d_in[6];
  P.Cre = (const __nv_bfloat16*)d_in[7];
  P.Cim = (const __nv_bfloat16*)d_in[8];
  P.logdt = (const __nv_bfloat16*)d_in[9];
  P.Dskip = (const __nv_bfloat16*)d_in[10];
  P.out = (__nv_bfloat16*)d_out;
  cudaFuncSetAttribute(fused_kernel, cudaFuncAttributeMaxDynamicSharedMemorySize, SMEM_BYTES);
  fused_kernel<<<NCTA, NTHREADS, SMEM_BYTES>>>(P, mx, mw, mo, mu, mout);
}
```

```cpp
#include <cuda_runtime.h>
#include <cuda_bf16.h>
#include <cuda_fp16.h>
#include <cuda.h>
#include <stdint.h>

#define DBG_TS 0

namespace {

constexpr int NTHREADS = 512;
constexpr int NCTA = 128;
constexpr int OFF_W = 0;
constexpr int OFF_X = 98304;
constexpr int OFF_U = OFF_X + 65536;
constexpr int U_CH = 4416, U_ODD = 2240, U_PAD = 128;
constexpr int OFF_STG0 = OFF_U + 18432;
constexpr int OFF_T = OFF_STG0 + 24576;
constexpr int T_CH = 5216;
constexpr int T_D = 0;
constexpr int T_5 = 2144;
constexpr int T_3 = T_5 + 384;
constexpr int T_7 = T_5 + 1024;
constexpr int T_9 = T_7 + 320;
constexpr int T_KC = T_9 + 320;
constexpr int T_ST = T_5 - 1024;
constexpr int OFF_PHI = OFF_T + 4 * T_CH;
constexpr int OFF_BAR = OFF_PHI + 1024;
constexpr int OFF_XP = OFF_BAR + 496;
constexpr int SMEM_BYTES = OFF_BAR + 512;
constexpr uint32_t SB = 1024;
static_assert(T_KC + 2 * 656 <= T_CH, "table size");
static_assert(SMEM_BYTES <= 232448, "smem");
constexpr int MB_URAW = 0, MB_FULL = 1  , MB_WO = 17  , MB_UFULL = 19,
              MB_EMPTY = 21  , MB_CLOSE = 37;
__host__ __device__ constexpr uint32_t BAR(int i) { return SB + OFF_BAR + 8 * i; }
constexpr int NB_WG0 = 1, NB_KPART = 2, NB_ST0 = 3  , NB_KV = 5, NB_RED = 6, NB_INIT = 7, NB_PREP = 8, NB_PROD = 9, NB_RDY = 10, NB_BDONE = 11, NB_ZERO = 12;
#define ZERO_N 1024
#define ZERO_STEP 3
#define STEPU 0
#define STEPPF 0
constexpr int STEP_PF = STEPPF, STEP_U = STEPU;
constexpr int SPIN_MAX = 1 << 16;

__device__ unsigned g_cnt[8 * 32];
__device__ uint4 g_uT[512 * 256];
constexpr int X_PART = 0;
constexpr int X_O = 16 * 8 * 144;
constexpr int X_Y = X_O + 32 * 32 * 128;
constexpr int X_SIZE = X_Y + 512 * 8 * 32;
__device__ uint4 g_x[2 * X_SIZE];
extern __shared__ uint8_t smem_raw[];
#define TS(i) do {} while (0)
#define TS1(i) do {} while (0)
#define GT(i) do {} while (0)

__device__ __forceinline__ uint32_t smem_u32(const void* p) { return (uint32_t)__cvta_generic_to_shared(p); }
__device__ __forceinline__ void mbar_arrive(uint32_t b) {
  asm volatile("mbarrier.arrive.shared::cta.b64 _, [%0];" ::"r"(b) : "memory");
}
__device__ __forceinline__ void mbar_wait(uint32_t b) {
  uint32_t done = 0;
#pragma unroll 1
  for (int i = 0; i < SPIN_MAX && !done; i++) {
    asm volatile("{\n.reg .pred p;\nmbarrier.try_wait.parity.shared::cta.b64 p, [%1], 0, 4000;\nselp.u32 %0, 1, 0, p;\n}\n"
                 : "=r"(done) : "r"(b) : "memory");
  }
}
__device__ __forceinline__ void mbar_init(uint32_t b, int n) {
  asm volatile("mbarrier.init.shared::cta.b64 [%0], %1;" ::"r"(b), "r"(n) : "memory");
}
__device__ __forceinline__ void mbar_expect(uint32_t b, int bytes) {
  asm volatile("mbarrier.arrive.expect_tx.shared::cta.b64 _, [%0], %1;" ::"r"(b), "r"(bytes) : "memory");
}
__device__ __forceinline__ void nb_sync(int id, int n) { asm volatile("bar.sync %0, %1;" ::"r"(id), "r"(n) : "memory"); }
__device__ __forceinline__ void nb_arrive(int id, int n) { asm volatile("bar.arrive %0, %1;" ::"r"(id), "r"(n) : "memory"); }
#define ELECT "{\n.reg .pred p;\nelect.sync _|p, 0xffffffff;\n@p "
__device__ __forceinline__ void e_expect(uint32_t b, int bytes) {
  asm volatile(ELECT "mbarrier.arrive.expect_tx.shared::cta.b64 _, [%0], %1;\n}\n" ::"r"(b), "r"(bytes) : "memory");
}
__device__ __forceinline__ void e_tma2d(uint32_t dst, const CUtensorMap* m, uint32_t bar, int c0, int c1) {
  asm volatile(ELECT "cp.async.bulk.tensor.2d.shared::cluster.global.mbarrier::complete_tx::bytes [%0], [%1, {%3,%4}], [%2];\n}\n"
               ::"r"(dst), "l"(m), "r"(bar), "r"(c0), "r"(c1) : "memory");
}
__device__ __forceinline__ void e_tma3d(uint32_t dst, const CUtensorMap* m, uint32_t bar, int c0, int c1, int c2) {
  asm volatile(ELECT "cp.async.bulk.tensor.3d.shared::cluster.global.mbarrier::complete_tx::bytes [%0], [%1, {%3,%4,%5}], [%2];\n}\n"
               ::"r"(dst), "l"(m), "r"(bar), "r"(c0), "r"(c1), "r"(c2) : "memory");
}
__device__ __forceinline__ void e_tma5d(uint32_t dst, const CUtensorMap* m, uint32_t bar, int c0, int c4) {
  asm volatile(ELECT "cp.async.bulk.tensor.5d.shared::cluster.global.mbarrier::complete_tx::bytes [%0], [%1, {%3,%5,%5,%5,%4}], [%2];\n}\n"
               ::"r"(dst), "l"(m), "r"(bar), "r"(c0), "r"(c4), "r"(0) : "memory");
}
__device__ __forceinline__ void e_bulk(uint32_t dst, const void* src, int bytes, uint32_t bar) {
  asm volatile(ELECT "cp.async.bulk.shared::cluster.global.mbarrier::complete_tx::bytes [%0], [%1], %2, [%3];\n}\n"
               ::"r"(dst), "l"(src), "r"(bytes), "r"(bar) : "memory");
}
__device__ __forceinline__ void e_prefetch(const void* p, int bytes) {
  asm volatile(ELECT "cp.async.bulk.prefetch.L2.global [%0], %1;\n}\n" ::"l"(p), "r"(bytes) : "memory");
}
__device__ __forceinline__ void e_store2d(const CUtensorMap* m, uint32_t src, int c0, int c1) {
  asm volatile(ELECT "cp.async.bulk.tensor.2d.global.shared::cta.bulk_group [%0, {%2,%3}], [%1];\n"
               "@p cp.async.bulk.commit_group;\n@p cp.async.bulk.wait_group.read 0;\n}\n"
               ::"l"(m), "r"(src), "r"(c0), "r"(c1) : "memory");
}
__host__ __device__ constexpr uint64_t mkdesc(uint32_t addr, uint32_t lbo, uint32_t sbo, int swz) {
  return (uint64_t)((addr & 0x3FFFF) >> 4) | ((uint64_t)(lbo >> 4) << 16) | ((uint64_t)(sbo >> 4) << 32) |
         ((uint64_t)swz << 62);
}
#define WG_FENCE() asm volatile("wgmma.fence.sync.aligned;" ::: "memory")
#define WG_COMMIT() asm volatile("wgmma.commit_group.sync.aligned;" ::: "memory")
#define WG_WAIT(n) asm volatile("wgmma.wait_group.sync.aligned " #n ";" ::: "memory")

__device__ __forceinline__ void mma(float& d0, float& d1, float& d2, float& d3, uint32_t a0, uint32_t a1, uint32_t a2,
                                    uint32_t a3, uint32_t b0, uint32_t b1) {
  asm volatile("mma.sync.aligned.m16n8k16.row.col.f32.bf16.bf16.f32 {%0,%1,%2,%3},{%4,%5,%6,%7},{%8,%9},{%0,%1,%2,%3};"
               : "+f"(d0), "+f"(d1), "+f"(d2), "+f"(d3)
               : "r"(a0), "r"(a1), "r"(a2), "r"(a3), "r"(b0), "r"(b1));
}
__device__ __forceinline__ void mmac(float (&d)[4], uint32_t a0, uint32_t a1, uint32_t a2, uint32_t a3, uint32_t b0,
                                     uint32_t b1, const float (&c)[4]) {
  asm volatile("mma.sync.aligned.m16n8k16.row.col.f32.bf16.bf16.f32 {%0,%1,%2,%3},{%4,%5,%6,%7},{%8,%9},{%10,%11,%12,%13};"
               : "=f"(d[0]), "=f"(d[1]), "=f"(d[2]), "=f"(d[3])
               : "r"(a0), "r"(a1), "r"(a2), "r"(a3), "r"(b0), "r"(b1), "f"(c[0]), "f"(c[1]), "f"(c[2]), "f"(c[3]));
}
__device__ __forceinline__ void mma_p(int p, float (&d)[4], uint32_t a0, uint32_t a1, uint32_t a2, uint32_t a3, uint32_t b0, uint32_t b1) {
  asm volatile("{\n.reg .pred q;\nsetp.ne.b32 q, %10, 0;\n"
               "@q mma.sync.aligned.m16n8k16.row.col.f32.bf16.bf16.f32 {%0,%1,%2,%3},{%4,%5,%6,%7},{%8,%9},{%0,%1,%2,%3};\n}\n"
               : "+f"(d[0]), "+f"(d[1]), "+f"(d[2]), "+f"(d[3])
               : "r"(a0), "r"(a1), "r"(a2), "r"(a3), "r"(b0), "r"(b1), "r"(p));
}
__device__ __forceinline__ void mmac_p(int p, float (&d)[4], uint32_t a0, uint32_t a1, uint32_t a2, uint32_t a3, uint32_t b0,
                                       uint32_t b1, const float (&c)[4]) {
  asm volatile("{\n.reg .pred q;\nsetp.ne.b32 q, %14, 0;\n"
               "@q mma.sync.aligned.m16n8k16.row.col.f32.bf16.bf16.f32 {%0,%1,%2,%3},{%4,%5,%6,%7},{%8,%9},{%10,%11,%12,%13};\n}\n"
               : "+f"(d[0]), "+f"(d[1]), "+f"(d[2]), "+f"(d[3])
               : "r"(a0), "r"(a1), "r"(a2), "r"(a3), "r"(b0), "r"(b1), "f"(c[0]), "f"(c[1]), "f"(c[2]), "f"(c[3]), "r"(p));
}
__device__ __forceinline__ void mma_k8(float (&d)[4], uint32_t a0, uint32_t a1, uint32_t b0) {
  asm volatile("mma.sync.aligned.m16n8k8.row.col.f32.bf16.bf16.f32 {%0,%1,%2,%3},{%4,%5},{%6},{%0,%1,%2,%3};"
               : "+f"(d[0]), "+f"(d[1]), "+f"(d[2]), "+f"(d[3]) : "r"(a0), "r"(a1), "r"(b0));
}
__device__ __forceinline__ void mma0(float& d0, float& d1, float& d2, float& d3, uint32_t a0, uint32_t a1, uint32_t a2,
                                     uint32_t a3, uint32_t b0, uint32_t b1) {
  asm volatile("mma.sync.aligned.m16n8k16.row.col.f32.bf16.bf16.f32 {%0,%1,%2,%3},{%4,%5,%6,%7},{%8,%9},{%10,%10,%10,%10};"
               : "=f"(d0), "=f"(d1), "=f"(d2), "=f"(d3)
               : "r"(a0), "r"(a1), "r"(a2), "r"(a3), "r"(b0), "r"(b1), "f"(0.f));
}
__device__ __forceinline__ uint32_t pack_bf(float lo, float hi) {
  uint32_t r;
  asm("cvt.rn.bf16x2.f32 %0, %1, %2;" : "=r"(r) : "f"(hi), "f"(lo));
  return r;
}
__device__ __forceinline__ float bf_lo(uint32_t w) { return __uint_as_float(w << 16); }
__device__ __forceinline__ float bf_hi(uint32_t w) { return __uint_as_float(w & 0xffff0000u); }
__device__ __forceinline__ float bf_round(float x) { return __bfloat162float(__float2bfloat16_rn(x)); }
__device__ __forceinline__ uint32_t bmax2(uint32_t a, uint32_t b) {
  uint32_t r; asm("max.bf16x2 %0, %1, %2;" : "=r"(r) : "r"(a), "r"(b)); return r;
}
__device__ __forceinline__ uint32_t bmin2(uint32_t a, uint32_t b) {
  uint32_t r; asm("min.bf16x2 %0, %1, %2;" : "=r"(r) : "r"(a), "r"(b)); return r;
}
__device__ __forceinline__ float ex2(float x) { float r; asm("ex2.approx.ftz.f32 %0, %1;" : "=f"(r) : "f"(x)); return r; }
__device__ __forceinline__ float rcp(float x) { float r; asm("rcp.approx.ftz.f32 %0, %1;" : "=f"(r) : "f"(x)); return r; }
__device__ __forceinline__ void ldsm4(uint32_t (&r)[4], uint32_t a) {
  asm volatile("ldmatrix.sync.aligned.m8n8.x4.shared.b16 {%0,%1,%2,%3}, [%4];"
               : "=r"(r[0]), "=r"(r[1]), "=r"(r[2]), "=r"(r[3]) : "r"(a) : "memory");
}
__device__ __forceinline__ void ldsm4t(uint32_t (&r)[4], uint32_t a) {
  asm volatile("ldmatrix.sync.aligned.m8n8.x4.trans.shared.b16 {%0,%1,%2,%3}, [%4];"
               : "=r"(r[0]), "=r"(r[1]), "=r"(r[2]), "=r"(r[3]) : "r"(a) : "memory");
}
__device__ __forceinline__ void stsm4(uint32_t a, uint32_t r0, uint32_t r1, uint32_t r2, uint32_t r3) {
  asm volatile("stmatrix.sync.aligned.m8n8.x4.shared.b16 [%0], {%1,%2,%3,%4};"
               ::"r"(a), "r"(r0), "r"(r1), "r"(r2), "r"(r3) : "memory");
}
__device__ __forceinline__ uint32_t lds32(uint32_t a) {
  uint32_t r; asm volatile("ld.shared.u32 %0, [%1];" : "=r"(r) : "r"(a) : "memory"); return r;
}
__device__ __forceinline__ uint32_t lds16(uint32_t a) {
  uint32_t r; asm volatile("{\n.reg .u16 h;\nld.shared.u16 h, [%1];\ncvt.u32.u16 %0, h;\n}\n" : "=r"(r) : "r"(a) : "memory"); return r;
}
__device__ __forceinline__ uint2 lds64(uint32_t a) {
  uint2 r; asm volatile("ld.shared.v2.u32 {%0,%1}, [%2];" : "=r"(r.x), "=r"(r.y) : "r"(a) : "memory"); return r;
}
__device__ __forceinline__ uint4 lds128(uint32_t a) {
  uint4 r;
  asm volatile("ld.shared.v4.u32 {%0,%1,%2,%3}, [%4];" : "=r"(r.x), "=r"(r.y), "=r"(r.z), "=r"(r.w) : "r"(a) : "memory");
  return r;
}
__device__ __forceinline__ void sts32(uint32_t a, uint32_t v) { asm volatile("st.shared.u32 [%0], %1;" ::"r"(a), "r"(v) : "memory"); }
__device__ __forceinline__ void sts16(uint32_t a, uint32_t v) {
  asm volatile("{\n.reg .u16 h;\ncvt.u16.u32 h, %1;\nst.shared.u16 [%0], h;\n}\n" ::"r"(a), "r"(v) : "memory");
}
__device__ __forceinline__ void sts64(uint32_t a, uint32_t x, uint32_t y) {
  asm volatile("st.shared.v2.u32 [%0], {%1,%2};" ::"r"(a), "r"(x), "r"(y) : "memory");
}
__device__ __forceinline__ void sts128(uint32_t a, uint32_t x, uint32_t y, uint32_t z, uint32_t w) {
  asm volatile("st.shared.v4.u32 [%0], {%1,%2,%3,%4};" ::"r"(a), "r"(x), "r"(y), "r"(z), "r"(w) : "memory");
}
__device__ __forceinline__ uint4 ld_x(const uint4* p) {
  uint4 r;
  asm volatile("{\n.reg .b128 t;\nld.relaxed.gpu.global.b128 t, [%4];\nmov.b128 {%0,%1,%2,%3}, t;\n}\n"
               : "=r"(r.x), "=r"(r.y), "=r"(r.z), "=r"(r.w) : "l"(p) : "memory");
  return r;
}
__device__ __forceinline__ uint32_t ld_x32(const uint32_t* p) {
  uint32_t r; asm volatile("ld.relaxed.gpu.global.u32 %0, [%1];" : "=r"(r) : "l"(p) : "memory"); return r;
}
__device__ __forceinline__ void st_x(uint4* p, uint32_t x, uint32_t y, uint32_t z, uint32_t w) {
  asm volatile("{\n.reg .b128 t;\nmov.b128 t, {%1,%2,%3,%4};\nst.relaxed.gpu.global.b128 [%0], t;\n}\n"
               ::"l"(p), "r"(x), "r"(y), "r"(z), "r"(w) : "memory");
}
__device__ __forceinline__ void st_x_p(int p, uint4* a, uint32_t x, uint32_t y, uint32_t z, uint32_t w) {
  asm volatile("{\n.reg .b128 t;\n.reg .pred q;\nsetp.ne.b32 q, %5, 0;\nmov.b128 t, {%1,%2,%3,%4};\n@q st.relaxed.gpu.global.b128 [%0], t;\n}\n"
               ::"l"(a), "r"(x), "r"(y), "r"(z), "r"(w), "r"(p) : "memory");
}
__device__ __forceinline__ void sts64_p(int p, uint32_t a, uint32_t x, uint32_t y) {
  asm volatile("{\n.reg .pred q;\nsetp.ne.b32 q, %3, 0;\n@q st.shared.v2.u32 [%0], {%1,%2};\n}\n" ::"r"(a), "r"(x), "r"(y), "r"(p) : "memory");
}
__device__ __forceinline__ void st_x32(uint32_t* p, uint32_t x) {
  asm volatile("st.relaxed.gpu.global.u32 [%0], %1;" ::"l"(p), "r"(x) : "memory");
}
__device__ __forceinline__ uint4* xbuf() {
  const uint2 v = lds64(SB + OFF_XP);
  return (uint4*)(((uint64_t)v.y << 32) | v.x);
}
__device__ __forceinline__ uint32_t nz(uint32_t w) { return max(w, 1u); }
__device__ __forceinline__ uint32_t fu(float x) { return __float_as_uint(x); }
__device__ __forceinline__ float uf(uint32_t x) { return __uint_as_float(x); }

__device__ __forceinline__ void wgmma_ss_n96(float (&d)[48], uint64_t da, uint64_t db, int sc) {
  asm volatile("{\n.reg .pred p;\nsetp.ne.b32 p, %50, 0;\n"
      "wgmma.mma_async.sync.aligned.m64n96k16.f32.bf16.bf16 "
      "{%0,%1,%2,%3,%4,%5,%6,%7,%8,%9,%10,%11,%12,%13,%14,%15,%16,%17,%18,%19,%20,%21,%22,%23,%24,%25,%26,%27,%28,%29,%30,%31,%32,%33,%34,%35,%36,%37,%38,%39,%40,%41,%42,%43,%44,%45,%46,%47}, "
      "%48, %49, p, 1, 1, 0, 1;\n}\n"
      : "+f"(d[0]), "+f"(d[1]), "+f"(d[2]), "+f"(d[3]), "+f"(d[4]), "+f"(d[5]), "+f"(d[6]), "+f"(d[7]),
        "+f"(d[8]), "+f"(d[9]), "+f"(d[10]), "+f"(d[11]), "+f"(d[12]), "+f"(d[13]), "+f"(d[14]), "+f"(d[15]),
        "+f"(d[16]), "+f"(d[17]), "+f"(d[18]), "+f"(d[19]), "+f"(d[20]), "+f"(d[21]), "+f"(d[22]), "+f"(d[23]),
        "+f"(d[24]), "+f"(d[25]), "+f"(d[26]), "+f"(d[27]), "+f"(d[28]), "+f"(d[29]), "+f"(d[30]), "+f"(d[31]),
        "+f"(d[32]), "+f"(d[33]), "+f"(d[34]), "+f"(d[35]), "+f"(d[36]), "+f"(d[37]), "+f"(d[38]), "+f"(d[39]),
        "+f"(d[40]), "+f"(d[41]), "+f"(d[42]), "+f"(d[43]), "+f"(d[44]), "+f"(d[45]), "+f"(d[46]), "+f"(d[47])
      : "l"(da), "l"(db), "r"(sc));
}

__device__ __forceinline__ void wgmma_rs_n128(float (&d)[64], const uint4& a, uint64_t db, int sc) {
  asm volatile("{\n.reg .pred p;\nsetp.ne.b32 p, %69, 0;\n"
      "wgmma.mma_async.sync.aligned.m64n128k16.f32.bf16.bf16 "
      "{%0,%1,%2,%3,%4,%5,%6,%7,%8,%9,%10,%11,%12,%13,%14,%15,%16,%17,%18,%19,%20,%21,%22,%23,%24,%25,%26,%27,%28,%29,%30,%31,%32,%33,%34,%35,%36,%37,%38,%39,%40,%41,%42,%43,%44,%45,%46,%47,%48,%49,%50,%51,%52,%53,%54,%55,%56,%57,%58,%59,%60,%61,%62,%63}, "
      "{%64,%65,%66,%67}, %68, p, 1, 1, 1;\n}\n"
      : "+f"(d[0]), "+f"(d[1]), "+f"(d[2]), "+f"(d[3]), "+f"(d[4]), "+f"(d[5]), "+f"(d[6]), "+f"(d[7]),
        "+f"(d[8]), "+f"(d[9]), "+f"(d[10]), "+f"(d[11]), "+f"(d[12]), "+f"(d[13]), "+f"(d[14]), "+f"(d[15]),
        "+f"(d[16]), "+f"(d[17]), "+f"(d[18]), "+f"(d[19]), "+f"(d[20]), "+f"(d[21]), "+f"(d[22]), "+f"(d[23]),
        "+f"(d[24]), "+f"(d[25]), "+f"(d[26]), "+f"(d[27]), "+f"(d[28]), "+f"(d[29]), "+f"(d[30]), "+f"(d[31]),
        "+f"(d[32]), "+f"(d[33]), "+f"(d[34]), "+f"(d[35]), "+f"(d[36]), "+f"(d[37]), "+f"(d[38]), "+f"(d[39]),
        "+f"(d[40]), "+f"(d[41]), "+f"(d[42]), "+f"(d[43]), "+f"(d[44]), "+f"(d[45]), "+f"(d[46]), "+f"(d[47]),
        "+f"(d[48]), "+f"(d[49]), "+f"(d[50]), "+f"(d[51]), "+f"(d[52]), "+f"(d[53]), "+f"(d[54]), "+f"(d[55]),
        "+f"(d[56]), "+f"(d[57]), "+f"(d[58]), "+f"(d[59]), "+f"(d[60]), "+f"(d[61]), "+f"(d[62]), "+f"(d[63])
      : "r"(a.x), "r"(a.y), "r"(a.z), "r"(a.w), "l"(db), "r"(sc));
}

struct Params {
  const __nv_bfloat16 *x, *wphi, *wo, *u, *logA, *Aim, *Cre, *Cim, *logdt, *Dskip;
  __nv_bfloat16* out;
};

__device__ __forceinline__ uint4 tr_row(const uint4 (&v)[8], int i) {
  uint32_t o[4];
#pragma unroll
  for (int m = 0; m < 4; m++) {
    const uint4 &ra = v[2 * m], &rb = v[2 * m + 1];
    const int k = i >> 1;
    const uint32_t xa = k == 0 ? ra.x : k == 1 ? ra.y : k == 2 ? ra.z : ra.w;
    const uint32_t xb = k == 0 ? rb.x : k == 1 ? rb.y : k == 2 ? rb.z : rb.w;
    o[m] = __byte_perm(xa, xb, (i & 1) ? 0x7632 : 0x5410);
  }
  return make_uint4(o[0], o[1], o[2], o[3]);
}

struct cpx { float r, i; };
__device__ __forceinline__ cpx cmul(cpx a, cpx b) { return {a.r * b.r - a.i * b.i, a.r * b.i + a.i * b.r}; }
__device__ __forceinline__ cpx csq(cpx a) { return {a.r * a.r - a.i * a.i, 2.f * (a.r * a.i)}; }
__device__ __forceinline__ cpx polar(float e, float t) {
  const float m = ex2(e);
  return {m * __cosf(t), m * __sinf(t)};
}

struct KgenRaw { unsigned short la, ai, cr, ci, ldt; };
__device__ __forceinline__ KgenRaw kgen_load(const Params& P, int d, int unit, int lane) {
  const int o = d * 128 + unit * 32 + lane;
  return {__ldg((const unsigned short*)P.logA + o), __ldg((const unsigned short*)P.Aim + o), __ldg((const unsigned short*)P.Cre + o),
          __ldg((const unsigned short*)P.Cim + o), __ldg((const unsigned short*)P.logdt + d)};
}
__device__ __forceinline__ void kgen_unit(const KgenRaw& r, int lane, uint32_t buf, uint32_t open_bar, float& dt,
                                          float (&k)[5][4], float& k2048) {
  dt = bf_round(expf(bf_lo(r.ldt)));
  const float a2 = -(bf_round(expf(bf_lo(r.la))) * dt) * 1.4426950408889634f;
  const float f = bf_lo(r.ai) * dt;
  const float r128 = f * 20.371832715762604f;
  const cpx C = {bf_lo(r.cr), -bf_lo(r.ci)};
  const uint32_t sa = buf + (lane & 7) * 128 + ((((lane >> 3) ^ lane) & 7) << 4);
  const uint32_t lb = buf + (lane >> 3) * 128 + (((lane ^ (lane >> 3)) & 7) << 4);
  const uint32_t la = buf + ((lane >> 3) & 1) * 1024 + (lane >> 4) * 128 + (((lane ^ (lane >> 4)) & 7) << 4);
  auto put = [&](const cpx (&v)[8], uint32_t off) {
    stsm4(sa + off, pack_bf(v[0].r, v[0].i), pack_bf(v[1].r, v[1].i), pack_bf(v[2].r, v[2].i), pack_bf(v[3].r, v[3].i));
    stsm4((sa ^ 64) + off, pack_bf(v[4].r, v[4].i), pack_bf(v[5].r, v[5].i), pack_bf(v[6].r, v[6].i), pack_bf(v[7].r, v[7].i));
  };
  uint32_t A[4][4], B[5][2][4];
  auto getB = [&](int j, uint32_t off) {
    __syncwarp();
    ldsm4(B[j][0], lb + off);
    ldsm4(B[j][1], (lb ^ 64) + 512 + off);
  };
  cpx t0[8], t1[8], t2[8], t3[8], t4[8];
  t0[0] = {1.f, 0.f};
  t0[1] = polar(a2, f);
  t1[0] = polar(a2 * 128.f, (r128 - rintf(r128)) * 6.283185307179586f);
  t0[2] = csq(t0[1]); t0[4] = csq(t0[2]);
  t2[0] = csq(t1[0]); t3[0] = csq(t2[0]); t4[0] = csq(t3[0]);
  t0[3] = cmul(t0[2], t0[1]); t0[5] = cmul(t0[4], t0[1]); t0[6] = cmul(t0[4], t0[2]); t0[7] = cmul(t0[4], t0[3]);
  put(t0, 0); getB(0, 0);
  {
    cpx w8 = csq(t0[4]);
    w8.i = -w8.i;
    const cpx w16 = csq(w8), w32 = csq(w16), w64 = csq(w32);
    cpx a[8];
    a[0] = C; a[1] = cmul(C, w8);
    a[2] = cmul(a[0], w16); a[3] = cmul(a[1], w16);
#pragma unroll
    for (int i = 0; i < 4; i++) a[4 + i] = cmul(a[i], w32);
    put(a, 0);
#pragma unroll
    for (int i = 0; i < 8; i++) a[i] = cmul(a[i], w64);
    put(a, 1024);
    __syncwarp();
#pragma unroll
    for (int s = 0; s < 4; s++) ldsm4(A[s], (la ^ (s << 5)) + s * 256);
  }
#pragma unroll
  for (int i = 1; i < 8; i++) t1[i] = cmul(t0[i], t1[0]);
  put(t1, 0); getB(1, 0);
#pragma unroll
  for (int i = 1; i < 8; i++) t2[i] = cmul((i & 1) ? t1[i & 6] : t0[i & 6], t2[0]);
  put(t2, 1024); getB(2, 1024);
#pragma unroll
  for (int i = 1; i < 8; i++) t3[i] = cmul((i & 2) ? t2[i & 5] : ((i & 1) ? t1[i & 4] : t0[i & 4]), t3[0]);
  put(t3, 0); getB(3, 0);
#pragma unroll
  for (int i = 1; i < 8; i++) t4[i] = cmul((i & 4) ? t3[i & 3] : ((i & 2) ? t2[i & 1] : t1[0]), t4[0]);
  put(t4, 1024); getB(4, 1024);
  const cpx we = csq(t4[0]);
  k2048 += C.r * we.r + C.i * we.i;
  if (open_bar) mbar_wait(open_bar);
#pragma unroll
  for (int s = 0; s < 4; s++)
#pragma unroll
    for (int j = 0; j < 5; j++)
      mma(k[j][0], k[j][1], k[j][2], k[j][3], A[s][0], A[s][1], A[s][2], A[s][3], B[j][s >> 1][2 * (s & 1)], B[j][s >> 1][2 * (s & 1) + 1]);
}

__device__ __forceinline__ void build_tables(uint32_t tb, int lane, float (&k)[5][4], float k2048) {
  const int g = lane >> 2, c = lane & 3;
  const uint32_t kc = tb + T_KC + 16;
  {
    const uint32_t a0 = kc + 16 * g + 4 * c, a2 = kc + 2 * (256 + 4 * g + c);
    const uint32_t a3 = kc + 2 * (384 + 2 * g + 64 * (c & 1) + (c >> 1)), a4 = kc + 2 * (512 + g + 32 * c);
#pragma unroll
    for (int r = 0; r < 2; r++) {
      sts32(a0 + 128 * r, pack_bf(k[0][2 * r], k[0][2 * r + 1]));
      sts32(a0 + 128 * r + 256, pack_bf(k[1][2 * r], k[1][2 * r + 1]));
      const uint32_t w2 = pack_bf(k[2][2 * r], k[2][2 * r + 1]);
      const uint32_t w3 = pack_bf(k[3][2 * r], k[3][2 * r + 1]);
      const uint32_t w4 = pack_bf(k[4][2 * r], k[4][2 * r + 1]);
      sts16(a2 + 64 * r, w2); sts16(a2 + 64 * r + 128, w2 >> 16);
      sts16(a3 + 32 * r, w3); sts16(a3 + 32 * r + 64, w3 >> 16);
      sts16(a4 + 16 * r, w4); sts16(a4 + 16 * r + 32, w4 >> 16);
    }
  }
  if (lane == 0) { sts16(kc + 2 * 640, pack_bf(k2048, 0.f)); sts16(kc - 2, 0); }
  __syncwarp();
  const uint32_t td = tb + T_D + 32;
  {
    const uint4 v = lds128(kc + 16 * lane);
    const uint32_t pv = lds16(kc + 16 * lane - 2);
    sts128(td + 32 * lane, __byte_perm(v.x, pv, 0x5410), __byte_perm(v.x, v.x, 0x1032), __byte_perm(v.y, v.x, 0x7610),
           __byte_perm(v.y, v.y, 0x1032));
    sts128(td + 32 * lane + 16, __byte_perm(v.z, v.y, 0x7610), __byte_perm(v.z, v.z, 0x1032),
           __byte_perm(v.w, v.z, 0x7610), __byte_perm(v.w, v.w, 0x1032));
  }
  {
    const uint2 v = lds64(kc + 512 + 8 * lane);
    const uint32_t k4 = lds16(kc + 512 + 8 * lane + 8);
    const uint32_t pv = lds16(kc + (lane == 0 ? 510 : 512 + 8 * lane));
    const uint32_t k22 = __byte_perm(v.y, v.y, 0x1010);
    sts128(td + 1024 + 32 * lane, __byte_perm(v.x, pv, 0x5410), __byte_perm(v.x, v.x, 0x1010),
           __byte_perm(v.x, v.x, 0x1032), __byte_perm(v.y, v.x, 0x7610));
    sts128(td + 1024 + 32 * lane + 16, k22, k22, __byte_perm(v.y, v.y, 0x1032), __byte_perm(k4, v.y, 0x7610));
  }
  {
    const uint32_t kk = lds16(kc + 2 * 384);
    const uint32_t w = lane < 3 ? (kk | (kk << 16)) : (lane == 3 ? (kk << 16) : 0u);
    if (lane < 24) sts32(td + 4 * (lane < 16 ? 512 + lane : lane - 24), w);
    const uint32_t lo_ = lds16(kc + 2 * 511), le_ = lds16(kc + 2 * 512);
    const uint32_t ja = tb + T_5 + (lane < 16 ? 4 * lane : 256 + 4 * lane);
    sts32(ja, lane == 16 ? (le_ << 16) : 0u);
    sts32(ja + 384, lane == 16 ? (lo_ << 16) : 0u);
    sts32(tb + (lane < 16 ? T_7 : T_9 - 64) + 4 * lane, 0u);
  }
#pragma unroll
  for (int s = 0; s < 2; s++) {
    const uint32_t b = kc + 2 * (s ? 512 : 384) + 8 * lane;
    const uint2 v = lds64(b);
    uint32_t em = lds16(b - 2), e0 = v.x;
    const uint32_t e4 = lds16(b + 8);
    if (lane == 0) { em = 0; e0 = 0; }
    sts64(tb + (s ? T_7 : T_3) + 64 + 8 * lane, __byte_perm(v.x, em, 0x5432), __byte_perm(v.y, v.x, 0x7632));
    sts64(tb + (s ? T_9 : T_5) + 64 + 8 * lane, __byte_perm(v.y, e0, 0x5410), __byte_perm(e4, v.y, 0x5410));
  }
  __syncwarp();
}

__device__ __forceinline__ uint32_t box2w(int lo, int n, int o) {
  return ((unsigned)(o - lo) < (unsigned)n ? 0x3F80u : 0u) | ((unsigned)(o + 1 - lo) < (unsigned)n ? 0x3F800000u : 0u);
}

__device__ __forceinline__ void conv_channel(uint32_t ub, uint32_t tb, int lane, uint4* ydst) {
  const int g = lane >> 2, c = lane & 3, x = g - 2 * c;
  const uint32_t st = tb + T_ST + lane * 8;
  const int mi = lane >> 3;
  const uint32_t qa = ub + U_PAD + 16 * (lane & 7) + ((mi == 0 || mi == 3) ? U_ODD : 0) - (mi == 0 ? 16 : 0);
  const uint32_t kv = lds16(tb + T_KC + 16 + 2 * 512);
  {
    const uint32_t hb = ub + U_PAD + (mi & 1) * U_ODD + 16 * ((lane >> 4) + (lane & 7)) - 16;
    const int oh = c < 2 ? 8 + 2 * c : 2 * c - 8;
    const uint32_t bx0 = box2w(g - 4, 9, 2 * c), bx1 = box2w(g - 3, 7, 2 * c), bx2 = box2w(g - 4, 9, oh), bx3 = box2w(g - 3, 7, oh);
    uint32_t f7[9], f9a[9], f9b[9];
    const uint32_t fa = tb + T_7 + 4 * (8 + x);
#pragma unroll
    for (int m = 0; m < 9; m++) {
      f7[m] = lds32(fa + 32 * m);
      f9b[m] = lds32(fa + 320 + 32 * m);
      f9a[m] = lds32(fa + 316 + 32 * m);
    }
    mbar_wait(BAR(MB_EMPTY + 15));
    TS(36);
    uint32_t z09[8], z07[8], zm9[8], zm7[8];
#pragma unroll
    for (int i = 0; i < 8; i++) {
      uint32_t h[4];
      ldsm4(h, hb + 128 * i);
      float y0, y1, y2, y3, w0, w1, w2, w3;
      mma0(y0, y1, y2, y3, bx0, bx1, bx2, bx3, h[2], c < 2 ? h[3] : h[1]);
      mma0(w0, w1, w2, w3, bx0, bx1, bx2, bx3, h[1], c < 2 ? h[2] : h[0]);
      z09[i] = pack_bf(y0, y1); z07[i] = pack_bf(y2, y3);
      zm9[i] = pack_bf(w0, w1); zm7[i] = pack_bf(w2, w3);
    }
    float a[4][2][4];
#pragma unroll
    for (int kap = 0; kap < 4; kap++)
#pragma unroll
      for (int sg = 0; sg < 2; sg++)
#pragma unroll
        for (int bk = 3; bk >= kap; bk--) {
          const int m = 2 * (bk - kap) + 1;
          float(&a0)[4] = a[bk][0];
          float(&a1)[4] = a[bk][1];
          if (sg == 0 && kap == 0) {
            mma0(a0[0], a0[1], a0[2], a0[3], f9a[m], f9a[m + 1], f9a[m - 1], f9a[m], z09[0], z09[1]);
            mma0(a1[0], a1[1], a1[2], a1[3], f9b[m], f9b[m + 1], f9b[m - 1], f9b[m], zm9[0], zm9[1]);
          } else if (sg == 0) {
            mma(a0[0], a0[1], a0[2], a0[3], f9a[m], f9a[m + 1], f9a[m - 1], f9a[m], z09[2 * kap], z09[2 * kap + 1]);
            mma(a1[0], a1[1], a1[2], a1[3], f9b[m], f9b[m + 1], f9b[m - 1], f9b[m], zm9[2 * kap], zm9[2 * kap + 1]);
          } else {
            mma(a0[0], a0[1], a0[2], a0[3], f7[m], f7[m + 1], f7[m - 1], f7[m], zm7[2 * kap], zm7[2 * kap + 1]);
            mma(a1[0], a1[1], a1[2], a1[3], f7[m], f7[m + 1], f7[m - 1], f7[m], z07[2 * kap], z07[2 * kap + 1]);
          }
        }
#pragma unroll
    for (int bk = 0; bk < 4; bk++) {
      sts64(st + 256 * (8 + 2 * bk), pack_bf(a[bk][0][0], a[bk][0][1]), pack_bf(a[bk][1][0], a[bk][1][1]));
      sts64(st + 256 * (9 + 2 * bk), pack_bf(a[bk][0][2], a[bk][0][3]), pack_bf(a[bk][1][2], a[bk][1][3]));
    }
  }
  TS(44);
  {
    const int oh = c < 3 ? 2 * c : -10;
    const uint32_t bx0 = box2w(g - 10, 5, 2 * c - 8), bx1 = box2w(g - 5, 3, 2 * c - 8), bx2 = box2w(g - 10, 5, oh), bx3 = box2w(g - 5, 3, oh);
    const uint32_t lb0 = ((unsigned)(x + 5) < 2u ? kv : 0u) | ((unsigned)(x + 4) < 2u ? kv << 16 : 0u);
    const uint32_t lb1 = ((unsigned)(x - 3) < 2u ? kv : 0u) | ((unsigned)(x - 4) < 2u ? kv << 16 : 0u);
    const int q0 = g - 1, q1 = c < 3 ? g : g - 2;
    uint32_t y0a = ub + U_PAD + (q0 & 1) * U_ODD + 16 * (q0 >> 1) + 4 * c;
    uint32_t y1a = ub + U_PAD + (q1 & 1) * U_ODD + 16 * (q1 >> 1) + 4 * c;
    uint2 a5[10], a3[10];
    const uint32_t aa = tb + T_5 + 4 * (8 + 2 * g - 2 * c);
#pragma unroll
    for (int m = 0; m < 10; m++) { a5[m] = lds64(aa + 32 * m); a3[m] = lds64(aa + 384 + 32 * m); }
    float T[6][4];
#pragma unroll
    for (int i = 0; i < 6; i++) T[i][0] = T[i][1] = T[i][2] = T[i][3] = 0.f;
    uint32_t x5[2] = {0, 0}, x3[2] = {0, 0}, yb[4], lq[4];
    uint32_t lqa = qa, sta = st + 256 * 8;
    uint2 sv;
    auto fetch = [&]() {
      yb[0] = lds32(y0a); yb[1] = lds32(y1a); yb[2] = lds32(y0a + 64); yb[3] = lds32(y1a + 64);
      ldsm4(lq, lqa);
      sv = lds64(min(sta, st + 256 * 15));
      y0a += 128; y1a += 128; lqa += 128; sta += 256;
    };
    fetch();
#pragma unroll 2
    for (int kap = -1; kap < 13; kap++) {
      float yn[2][4];
      mma0(yn[0][0], yn[0][1], yn[0][2], yn[0][3], bx0, bx1, bx2, bx3, yb[0], yb[1]);
      mma0(yn[1][0], yn[1][1], yn[1][2], yn[1][3], bx0, bx1, bx2, bx3, yb[2], yb[3]);
      sts64_p(kap > 0, sta - 256 * 7, pack_bf(T[0][0], T[0][1]), pack_bf(T[0][2], T[0][3]));
#pragma unroll
      for (int i = 0; i < 5; i++)
        mmac_p((unsigned)kap < 12u - i, T[i], a5[2 * i + 1].x, a5[2 * i + 1].y, a5[2 * i].x, a5[2 * i].y, x5[0], x5[1], T[i + 1]);
      const float ci[4] = {bf_lo(sv.x), bf_hi(sv.x), bf_lo(sv.y), bf_hi(sv.y)};
      mmac_p(kap < 7, T[5], lq[0], lq[1], lq[2], lq[3], lb0, lb1, ci);
      fetch();
#pragma unroll
      for (int i = 0; i < 5; i++)
        mma_p((unsigned)kap < 12u - i, T[i], a3[2 * i + 1].x, a3[2 * i + 1].y, a3[2 * i].x, a3[2 * i].y, x3[0], x3[1]);
#pragma unroll
      for (int hh = 0; hh < 2; hh++) { x5[hh] = pack_bf(yn[hh][0], yn[hh][1]); x3[hh] = pack_bf(yn[hh][2], yn[hh][3]); }
    }
  }
  TS(45);
  {
    uint32_t F[66];
    const uint32_t fa = tb + T_D + 32 + 4 * x;
#pragma unroll
    for (int m = 0; m < 66; m++) F[m] = lds32(fa + 32 * m);
    float T[5][4];
#pragma unroll
    for (int i = 0; i < 5; i++) T[i][0] = T[i][1] = T[i][2] = T[i][3] = 0.f;
    uint32_t qd[8][4], held[2] = {0, 0};
    uint32_t qp = qa + 128 * 15, sta = st + 256 * 14;
    uint4* yd = ydst + 19 * 16;
#pragma unroll
    for (int i = 0; i < 6; i++) ldsm4(qd[i], qp - 16 * i);
    uint2 sv = lds64(sta + 256);
    float ci[4] = {bf_lo(sv.x), bf_hi(sv.x), bf_lo(sv.y), bf_hi(sv.y)};
    TS(46);
#pragma unroll 2
    for (int be = 15; be >= 0; be--) {
#pragma unroll
      for (int k = 4; k >= 1; k--)
        mmac_p(be <= 15 - k, T[k], qd[0][0], qd[0][1], qd[0][2], qd[0][3], F[16 * k + 1], F[16 * k], T[k - 1]);
      mmac(T[0], qd[0][0], qd[0][1], qd[0][2], qd[0][3], F[1], F[0], ci);
      ldsm4(qd[6], qp - 16 * 6);
      ldsm4(qd[7], qp - 16 * 7);
      sv = lds64(sta);
#pragma unroll
      for (int i = 1; i < 8; i++) {
#pragma unroll
        for (int k = 3; k >= 0; k--)
          mma_p(k == 0 || be <= 15 - k, T[k], qd[i][0], qd[i][1], qd[i][2], qd[i][3], F[16 * k + 2 * i + 1], F[16 * k + 2 * i]);
        if (i < 7) ldsm4(qd[i - 1], qp - 128 - 16 * (i - 1));
        if (i == 2) {
          const uint32_t w0 = pack_bf(T[4][0], T[4][1]), w1 = pack_bf(T[4][2], T[4][3]);
          st_x_p(be <= 10 && !(be & 1), yd, nz(w0), w1, held[0], held[1]);
          held[0] = w0; held[1] = w1;
        }
        if (i == 4) {
          if (be <= 4) sv = make_uint2(0, 0);
          ci[0] = bf_lo(sv.x); ci[1] = bf_hi(sv.x); ci[2] = bf_lo(sv.y); ci[3] = bf_hi(sv.y);
        }
      }
      qp -= 128; sta -= 256; yd -= 16;
    }
#pragma unroll
    for (int B = 1; B >= 0; B--)
      st_x(ydst + B * 32, nz(pack_bf(T[2 * B][0], T[2 * B][1])), pack_bf(T[2 * B][2], T[2 * B][3]),
           pack_bf(T[2 * B + 1][0], T[2 * B + 1][1]), pack_bf(T[2 * B + 1][2], T[2 * B + 1][3]));
  }
}

__device__ __forceinline__ void feat(const float (&acc)[48], int j0, const uint32_t (&wf)[4], uint32_t* w) {
  const uint32_t a0 = pack_bf(acc[4 * j0], acc[4 * j0 + 1]), a1 = pack_bf(acc[4 * j0 + 2], acc[4 * j0 + 3]);
  const uint32_t a2 = pack_bf(acc[4 * j0 + 4], acc[4 * j0 + 5]), a3 = pack_bf(acc[4 * j0 + 6], acc[4 * j0 + 7]);
  float p[8];
  mma0(p[0], p[1], p[2], p[3], a0, a1, a2, a3, wf[0], wf[1]);
  mma0(p[4], p[5], p[6], p[7], a0, a1, a2, a3, wf[2], wf[3]);
  w[0] = pack_bf(p[0], p[2]); w[1] = pack_bf(p[1], p[3]); w[2] = pack_bf(p[4], p[6]); w[3] = pack_bf(p[5], p[7]);
}
__device__ __forceinline__ void dual_softmax(const uint32_t* w, uint32_t* e) {
  const float L = 1.44268798828125f;
  uint32_t mx = bmax2(bmax2(w[0], w[1]), bmax2(w[2], w[3]));
  uint32_t mn = bmin2(bmin2(w[0], w[1]), bmin2(w[2], w[3]));
  mx = bmax2(mx, __shfl_xor_sync(0xffffffffu, mx, 1));
  mn = bmin2(mn, __shfl_xor_sync(0xffffffffu, mn, 1));
  mx = bmax2(mx, __shfl_xor_sync(0xffffffffu, mx, 2));
  mn = bmin2(mn, __shfl_xor_sync(0xffffffffu, mn, 2));
  const float mx0 = bf_lo(mx) * -L, mx1 = bf_hi(mx) * -L, mn0 = bf_lo(mn) * L, mn1 = bf_hi(mn) * L;
  float ep[2][4], em[2][4];
#pragma unroll
  for (int i = 0; i < 4; i++) {
    const float x0 = bf_lo(w[i]), x1 = bf_hi(w[i]);
    ep[0][i] = ex2(fmaf(x0, L, mx0)); em[0][i] = ex2(fmaf(x0, -L, mn0));
    ep[1][i] = ex2(fmaf(x1, L, mx1)); em[1][i] = ex2(fmaf(x1, -L, mn1));
  }
  __half2 sp = __floats2half2_rn((ep[0][0] + ep[0][1]) + (ep[0][2] + ep[0][3]), (ep[1][0] + ep[1][1]) + (ep[1][2] + ep[1][3]));
  __half2 sm = __floats2half2_rn((em[0][0] + em[0][1]) + (em[0][2] + em[0][3]), (em[1][0] + em[1][1]) + (em[1][2] + em[1][3]));
  sp = __hadd2(sp, __shfl_xor_sync(0xffffffffu, sp, 1));
  sm = __hadd2(sm, __shfl_xor_sync(0xffffffffu, sm, 1));
  sp = __hadd2(sp, __shfl_xor_sync(0xffffffffu, sp, 2));
  sm = __hadd2(sm, __shfl_xor_sync(0xffffffffu, sm, 2));
  const float rp[2] = {rcp(__low2float(sp)), rcp(__high2float(sp))}, rm[2] = {rcp(__low2float(sm)), rcp(__high2float(sm))};
#pragma unroll
  for (int i = 0; i < 4; i++) {
    const int r = i & 1, k = i & 2;
    e[i] = pack_bf(ep[r][k] * rp[r], ep[r][k + 1] * rp[r]);
    e[4 + i] = pack_bf(em[r][k] * rm[r], em[r][k + 1] * rm[r]);
  }
}

__global__ void __launch_bounds__(NTHREADS, 1)
fused_kernel(const Params P, const __grid_constant__ CUtensorMap mx, const __grid_constant__ CUtensorMap mw,
             const __grid_constant__ CUtensorMap mo, const __grid_constant__ CUtensorMap mu,
             const __grid_constant__ CUtensorMap mout) {
  constexpr uint32_t sb = SB;
  const int tid = threadIdx.x, lane = tid & 31;
  const int warp = __shfl_sync(0xffffffffu, tid >> 5, 0);
  const int b = blockIdx.x, oct = b >> 3, i8 = b & 7;
  const int rt = oct < 8 ? oct : 15 - oct;
  const int hp = (oct >> 3) * 8 + i8;

  const int d = b * 4 + ((tid >> 5) & 3);
  KgenRaw raw = {}, raw3 = {};
  unsigned short dsk = 0;
  if (tid < 384) {
    asm volatile("prefetch.tensormap [%0];" ::"l"(&mu) : "memory");
    asm volatile("prefetch.tensormap [%0];" ::"l"(&mw) : "memory");
    asm volatile("prefetch.tensormap [%0];" ::"l"(&mx) : "memory");
    raw = kgen_load(P, d, tid >> 7, lane);
    raw3 = kgen_load(P, d, 3, lane);
    dsk = __ldg((const unsigned short*)P.Dskip + d);
  }
  if (warp >= 12) asm volatile("setmaxnreg.dec.sync.aligned.u32 32;");
  if (warp == 12) {
    if (lane == 0) {
#pragma unroll
      for (int i = 0; i < 9; i++) mbar_init(BAR(i), 1);
      asm volatile("fence.mbarrier_init.release.cluster;" ::: "memory");
    }
    __syncwarp();
    if (lane < 9) mbar_expect(BAR(0) + 8 * lane, lane == 0 ? 16384 : (lane < 8 ? 28672 : 29696));
    __syncwarp();
    nb_arrive(NB_PREP, 448);
#pragma unroll 1
    for (int kb = 0; kb < 8; kb++) {
      if (kb == STEP_U) e_tma5d(sb + OFF_STG0, &mu, BAR(MB_URAW), i8 * 64, oct * 4);
      e_tma3d(sb + OFF_W + kb * 12288, &mw, BAR(MB_FULL) + 8 * kb, hp * 32, kb * 64, 0);
      if (kb < 5) e_tma2d(sb + OFF_X + (kb < 2 ? kb + 3 : kb - 2) * 16384, &mx, BAR(MB_FULL) + 8 * kb, kb * 64, rt * 256);
    }
    if (smem_u32(smem_raw) != SB) __trap();
  }
  if (warp >= 12) {
    if (warp == 12) {
      nb_sync(NB_PROD, 64);
      e_prefetch(P.x + (size_t)(rt * 256 + hp * 16) * 512, 16384);
      e_bulk(sb + OFF_PHI, P.wphi + hp * 512, 1024, BAR(MB_FULL + 7));
      uint32_t slot = sb + OFF_X + 3 * 16384;
#pragma unroll 1
      for (int n = 0; n < 11; n++) {
        mbar_wait(BAR(MB_EMPTY) + 8 * n);
        const int m = n + 5;
        e_tma2d(slot, &mx, BAR(MB_FULL) + 8 * m, (m & 7) * 64, rt * 256 + (m >> 3) * 128);
        slot = slot == sb + OFF_X + 4 * 16384 ? sb + OFF_X : slot + 16384;
        if (n == 7) e_prefetch(P.wo + (size_t)b * 2048, 4096);
      }
#pragma unroll 1
      for (int i = 0; i < 8; i++) {
        mbar_wait(BAR(MB_EMPTY + 10) + 8 * ((0x54332100u >> (4 * i)) & 7));
        const int w0 = (0x54736210u >> (4 * i)) & 7;
        const int col = (hp & 3) * 128 + (w0 >> 2) * 64;
        e_tma2d(sb + OFF_W + w0 * 16384, &mo, BAR(MB_WO) + 8 * (w0 >> 2), col, w0 * 64);
        e_tma2d(sb + OFF_W + w0 * 16384 + 8192, &mo, BAR(MB_WO) + 8 * (w0 >> 2), col ^ 64, w0 * 64);
      }
    } else {
      if (warp == 13) {
        if (lane == 0) {
#pragma unroll
          for (int i = 9; i < 38; i++) mbar_init(BAR(i), i < MB_EMPTY ? 1 : (i < MB_CLOSE ? 4 : 12));
          asm volatile("fence.mbarrier_init.release.cluster;" ::: "memory");
        }
        __syncwarp();
        if (lane < 10) mbar_expect(BAR(MB_FULL + 8) + 8 * lane, lane < 8 ? 16384 : 65536);
        __syncwarp();
        nb_arrive(NB_PROD, 64);
        const unsigned cnt0 = ld_x32(g_cnt + i8 * 32);
        const uint64_t xp = (uint64_t)(g_x + ((cnt0 >> 4) & 1) * X_SIZE);
        sts64(sb + OFF_XP, (uint32_t)xp, (uint32_t)(xp >> 32));
        nb_arrive(NB_PREP, 448);
        nb_sync(NB_INIT, 160);
        if (lane == 0) TS1(49);
        if (lane == 0) asm volatile("red.release.gpu.global.add.u32 [%0], 1;" ::"l"(g_cnt + i8 * 32) : "memory");
        if (lane == 0) TS1(50);
        nb_arrive(NB_ZERO, 96);
#pragma unroll 1
        for (int i = 0; i < SPIN_MAX; i++) {
          unsigned v;
          asm volatile("ld.acquire.gpu.global.u32 %0, [%1];" : "=r"(v) : "l"(g_cnt + (b >> 4) * 32) : "memory");
          if ((int)(v - ((cnt0 & ~15u) + 16)) >= 0) break;
          __nanosleep(200);
        }
        if (lane == 0) TS1(51);
        asm volatile("fence.proxy.async.global;" ::: "memory");
        mbar_wait(BAR(MB_EMPTY + 11));
        sts128(sb + OFF_U + (lane >> 4) * U_CH + ((lane >> 3) & 1) * U_ODD + (lane & 7) * 16, 0, 0, 0, 0);
        sts128(sb + OFF_U + (2 + (lane >> 4)) * U_CH + ((lane >> 3) & 1) * U_ODD + (lane & 7) * 16, 0, 0, 0, 0);
        __syncwarp();
        e_expect(BAR(MB_UFULL), 16384);
#pragma unroll 1
        for (int i = 0; i < 8; i++)
          e_bulk(sb + OFF_U + (i >> 1) * U_CH + (i & 1) * U_ODD + U_PAD, g_uT + (size_t)(b * 8 + i) * 128, 2048, BAR(MB_UFULL));
      } else {
        nb_sync(NB_ZERO, 96);
        uint4* xn = g_x + (g_x + X_SIZE - xbuf()) + b * (X_SIZE / NCTA);
#pragma unroll 1
        for (int i = tid - 448; i < X_SIZE / NCTA; i += 64) xn[i] = make_uint4(0, 0, 0, 0);
        if (tid == 448) TS1(55);
      }
    }
    return;
  }

  asm volatile("setmaxnreg.inc.sync.aligned.u32 160;");
  const int wg = warp >> 2, w = warp & 3, t = tid & 127;
  const int g = lane >> 2, c = lane & 3;
  const uint32_t tb = sb + OFF_T + w * T_CH;
  {
    float k[5][4], k2048 = 0.f, dt;
#pragma unroll
    for (int j = 0; j < 5; j++) k[j][0] = k[j][1] = k[j][2] = k[j][3] = 0.f;
    const uint32_t kp = tb + (wg & 1) * 2608;
#pragma unroll 1
    for (int r = 0; r <= (wg >> 1); r++) {
      kgen_unit(raw, lane, wg == 2 ? sb + OFF_STG0 + 16384 + w * 2048 : (kp + 127) & ~127u, r ? BAR(MB_EMPTY + 7) : 0u, dt, k, k2048);
      raw = raw3;
      TS(40 + wg + r);
      if (r == 0) {
        if (wg != 2) {
#pragma unroll
          for (int j = 0; j < 5; j++) sts128(kp + j * 512 + lane * 16, fu(k[j][0]), fu(k[j][1]), fu(k[j][2]), fu(k[j][3]));
          k2048 += __shfl_xor_sync(0xffffffffu, k2048, 16);
          k2048 += __shfl_xor_sync(0xffffffffu, k2048, 8);
          if (lane < 8) sts32(kp + 2560 + lane * 4, fu(k2048));
        } else if ((fu(k[0][0]) & fu(k[1][0]) & fu(k[2][0]) & fu(k[3][0]) & fu(k[4][0])) == 0xffffffffu) {
          sts32(kp, 0);
        }
        nb_sync(NB_PREP, 448);
        if (wg == 2) {
#pragma unroll 1
          for (int q = 0; q < 2; q++) {
            const uint32_t src = tb + q * 2608;
#pragma unroll
            for (int j = 0; j < 5; j++) {
              const uint4 v = lds128(src + j * 512 + lane * 16);
              k[j][0] += uf(v.x); k[j][1] += uf(v.y); k[j][2] += uf(v.z); k[j][3] += uf(v.w);
            }
            if (lane < 8) k2048 += uf(lds32(src + 2560 + lane * 4));
          }
        }
      }
    }
    if (wg == 2) {
      if (lane == 0 && (fu(k[0][0]) & fu(k[1][0]) & fu(k[2][0]) & fu(k[3][0]) & fu(k[4][0])) != 0xffffffffu)
        mbar_arrive(BAR(MB_CLOSE));
      TS(34);
#pragma unroll
      for (int o2 = 16; o2; o2 >>= 1) k2048 += __shfl_xor_sync(0xffffffffu, k2048, o2);
      const float sc = 2.f * dt;
#pragma unroll
      for (int j = 0; j < 5; j++) { k[j][0] *= sc; k[j][1] *= sc; k[j][2] *= sc; k[j][3] *= sc; }
      k2048 *= sc;
      if (lane == 0) k[0][0] += bf_lo(dsk);
      build_tables(tb, lane, k, k2048);
      TS(35);
      mbar_wait(BAR(MB_UFULL));
      uint4* const g_y = xbuf() + X_Y;
      conv_channel(sb + OFF_U + w * U_CH, tb, lane, g_y + (size_t)d * 256 + lane);
      nb_arrive(NB_BDONE, 384);
      TS(37);
      const int lam = w * 8 + g;
      const uint4* src = g_y + (size_t)(oct * 32 + c * 8) * 256 + i8 * 32 + lam;
      uint4 v[8];
#pragma unroll 1
      for (int it = 0; it < SPIN_MAX; it++) {
        uint32_t m = 0xffffffffu;
#pragma unroll
        for (int i = 0; i < 8; i++) v[i] = ld_x(src + i * 256);
#pragma unroll
        for (int i = 0; i < 8; i++) m = min(m, v[i].x);
        if (__all_sync(0xffffffffu, m != 0)) break;
      }
      __nv_bfloat16* dst = P.out + (size_t)(i8 * 256 + (lam >> 2) * 16 + (lam & 3) * 2) * 1024 + 512 + oct * 32 + c * 8;
#pragma unroll
      for (int i = 0; i < 8; i++) *(uint4*)(dst + (size_t)((i >> 2) * 128 + ((i >> 1) & 1) * 8 + (i & 1)) * 1024) = tr_row(v, i);
      TS(38);
      GT(63);
      return;
    }
    if (wg == 1) {
      mbar_wait(BAR(MB_URAW));
      TS(48);
      uint4* dst = g_uT + (size_t)(i8 * 64 + g) * 256 + (c & 1) * 128 + oct * 8 + w * 2 + (c >> 1);
      uint32_t r[8][4];
#pragma unroll
      for (int i = 0; i < 8; i++) ldsm4t(r[i], sb + OFF_STG0 + w * 4096 + lane * 128 + (((i ^ lane) & 7) << 4));
#pragma unroll
      for (int i = 0; i < 8; i++) dst[i * 2048] = make_uint4(r[i][0], r[i][1], r[i][2], r[i][3]);
      nb_arrive(NB_INIT, 160);
      if (lane == 0) mbar_arrive(BAR(MB_CLOSE));
      mbar_wait(BAR(MB_CLOSE));
    }
    TS(wg * 16 + 1);
  }

  float acc[2][48];
  {
    uint32_t fb = BAR(MB_FULL) + 64 * wg;
    uint32_t da = (uint32_t)mkdesc(sb + OFF_X, 16, 0, 0) + (wg ? 1024 : 3072), db = (uint32_t)mkdesc(sb + OFF_W, 4096, 0, 0);
    constexpr uint64_t ha = mkdesc(0, 0, 1024, 1), hb = mkdesc(0, 0, 512, 2);
#pragma unroll 1
    for (int kb = 0; kb < 8; kb++) {
      mbar_wait(fb);
      if (kb == 0) TS(wg * 16 + 2);
      WG_FENCE();
#pragma unroll
      for (int k = 0; k < 4; k++) {
        wgmma_ss_n96(acc[0], ha | (da + 2 * k), hb | (db + 64 * k), k ? 1 : kb);
        wgmma_ss_n96(acc[1], ha | (da + 2 * k + 512), hb | (db + 64 * k), k ? 1 : kb);
      }
      WG_COMMIT();
      WG_WAIT(1);
      if (kb > 0 && lane == 0) mbar_arrive(fb + 8 * (MB_EMPTY - MB_FULL - 1));
      fb += 8; db += 768;
      da = da == (uint32_t)mkdesc(sb + OFF_X + 65536, 16, 0, 0) ? da - 4096 : da + 1024;
    }
    WG_WAIT(0);
    if (lane == 0) mbar_arrive(fb + 8 * (MB_EMPTY - MB_FULL - 1));
    mbar_wait(fb + 8 * (MB_EMPTY - MB_FULL - 1));
  }
  uint32_t wf[2][4];
  ldsm4t(wf[0], sb + OFF_PHI + (lane & 15) * 32 + (lane >> 4) * 16);
  ldsm4t(wf[1], sb + OFF_PHI + 512 + (lane & 15) * 32 + (lane >> 4) * 16);
  TS(wg * 16 + 3);

  uint32_t pw[32], eq[32];
#pragma unroll
  for (int u = 0; u < 4; u++)
#pragma unroll
    for (int h = 0; h < 2; h++) feat(acc[u & 1], (u < 2 ? 4 : 0) + 2 * h, wf[h], pw + 8 * u + 4 * h);
  {
    uint32_t all = 0xffffffffu;
#pragma unroll
    for (int i = 0; i < 16; i++) all &= pw[2 * i];
    if (wg == 0 && lane == 0 && all != 0xffffffffu) mbar_arrive(BAR(MB_CLOSE));
  }
  mbar_wait(BAR(MB_CLOSE));
  const uint32_t stg0 = sb + OFF_STG0, stg1 = sb + OFF_X + 32768;
  uint32_t sl = (wg ? stg1 : stg0) + w * 3072 + lane * 16;
#pragma unroll
  for (int mt = 0; mt < 2; mt++)
#pragma unroll
    for (int h = 0; h < 2; h++) {
      const float* a = acc[mt] + 32 + 8 * h;
      stsm4(sl + mt * 12288 + 2048 + h * 512, pack_bf(a[0], a[1]), pack_bf(a[2], a[3]), pack_bf(a[4], a[5]), pack_bf(a[6], a[7]));
    }
#pragma unroll 1
  for (int u = 0; u < 4; u++) {
#pragma unroll
    for (int i = 0; i < 16; i++) eq[i] = eq[16 + i];
    dual_softmax(pw, eq + 16);
    dual_softmax(pw + 4, eq + 24);
    if (u < 2) {
#pragma unroll
      for (int i = 0; i < 4; i++) stsm4(sl + i * 512, eq[16 + 4 * i], eq[17 + 4 * i], eq[18 + 4 * i], eq[19 + 4 * i]);
      if (wg) nb_arrive(NB_ST0 + u, 256);
      sl += 12288;
    }
#pragma unroll
    for (int i = 0; i < 24; i++) pw[i] = pw[i + 8];
  }
  TS(wg * 16 + 4);
  uint4* const g_part = xbuf();
  uint4* const g_o = g_part + X_O;
  const uint32_t kvs = stg0;
  if (wg == 0) {
    nb_sync(NB_WG0, 128);
    mbar_wait(BAR(MB_EMPTY + 15));
    float kv[12];
#pragma unroll
    for (int i = 0; i < 12; i++) kv[i] = 0.f;
    const int mi = lane >> 3;
    const uint32_t ao = w * 512 + (lane & 7) * 16 + ((mi & 1) * 2 + (mi >> 1)) * 128, bo = 2048 + (w >> 1) * 512 + lane * 16;
#pragma unroll 1
    for (int j = 0; j < 4; j++) {
      if (j >= 2) nb_sync(NB_ST0 + j - 2, 256);
      const uint32_t sg = (j >= 2 ? stg1 : stg0) + (j & 1) * 12288;
      uint32_t a[4][4], bb[4][4];
#pragma unroll
      for (int s = 0; s < 4; s++) { ldsm4t(a[s], sg + s * 3072 + ao); ldsm4t(bb[s], sg + s * 3072 + bo); }
#pragma unroll
      for (int s = 0; s < 4; s++) {
        mma(kv[0], kv[1], kv[2], kv[3], a[s][0], a[s][1], a[s][2], a[s][3], bb[s][0], bb[s][1]);
        mma(kv[4], kv[5], kv[6], kv[7], a[s][0], a[s][1], a[s][2], a[s][3], bb[s][2], bb[s][3]);
        mma(kv[8], kv[9], kv[10], kv[11], a[s][0], a[s][1], a[s][2], a[s][3], 0x3F803F80u, 0x3F803F80u);
      }
    }
    uint4* pp = g_part + (size_t)(hp * 8 + rt) * 144;
    st_x(pp + t, nz(pack_bf(kv[0], kv[1])), pack_bf(kv[2], kv[3]), pack_bf(kv[4], kv[5]), pack_bf(kv[6], kv[7]));
    if (c < 2) st_x32((uint32_t*)(pp + 128) + w * 16 + c * 8 + g, nz(fu(c ? kv[10] : kv[8])));
    TS(5);
    const uint4* ps = g_part + (size_t)hp * 8 * 144 + t;
    const uint32_t* zs = (const uint32_t*)(g_part + (size_t)(hp * 8 + (lane >> 4) * 4) * 144 + 128) + w * 16 + (lane & 15);
    uint4 v[8];
    uint32_t zv[4];
#pragma unroll 1
    for (int it = 0; it < SPIN_MAX; it++) {
#pragma unroll
      for (int i = 0; i < 8; i++) v[i] = ld_x(ps + i * 144);
#pragma unroll
      for (int i = 0; i < 4; i++) zv[i] = ld_x32(zs + i * 576);
      uint32_t m = min(min(zv[0], zv[1]), min(zv[2], zv[3]));
#pragma unroll
      for (int i = 0; i < 8; i++) m = min(m, v[i].x);
      if (__all_sync(0xffffffffu, m != 0)) break;
    }
    float s4[4][4];
#pragma unroll
    for (int i = 0; i < 4; i++) s4[i][0] = s4[i][1] = s4[i][2] = s4[i][3] = 0.f;
    const uint32_t eye = (g >> 1) == c ? ((g & 1) ? 0x3F800000u : 0x3F80u) : 0u;
#pragma unroll
    for (int r = 0; r < 8; r++) {
      mma_k8(s4[(r & 1) * 2], v[r].x, v[r].y, eye);
      mma_k8(s4[(r & 1) * 2 + 1], v[r].z, v[r].w, eye);
    }
    float s[8];
#pragma unroll
    for (int i = 0; i < 8; i++) s[i] = s4[i >> 2][i & 3] + s4[2 + (i >> 2)][i & 3];
    float zsum = (uf(zv[0]) + uf(zv[1])) + (uf(zv[2]) + uf(zv[3]));
    zsum += __shfl_xor_sync(0xffffffffu, zsum, 16);
    stsm4(kvs + w * 512 + lane * 16, pack_bf(s[0], s[1]), pack_bf(s[2], s[3]), pack_bf(s[4], s[5]), pack_bf(s[6], s[7]));
    if (lane < 16) sts16(kvs + 2048 + (w * 16 + lane) * 2, pack_bf(zsum, 0.f));
    TS(6);
  }
  nb_sync(NB_KV, 256);
  {
    uint32_t kb_[4][4], zb[8];
#pragma unroll
    for (int i = 0; i < 4; i++) ldsm4t(kb_[i], kvs + i * 512 + lane * 16);
#pragma unroll
    for (int i = 0; i < 8; i++) zb[i] = lds32(kvs + 2048 + i * 16 + c * 4);
    uint4* od = g_o + (size_t)((rt * 4 + wg * 2) * 32 + hp * 2) * 128 + t;
#pragma unroll 1
    for (int mt = 0; mt < 2; mt++) {
#pragma unroll
      for (int h = 0; h < 2; h++) {
        const uint32_t* e = eq + 8 * h;
        float n[8], dn[4];
        mma0(dn[0], dn[1], dn[2], dn[3], e[0], e[1], e[2], e[3], zb[4 * h], zb[4 * h + 1]);
        mma0(n[0], n[1], n[2], n[3], e[0], e[1], e[2], e[3], kb_[2 * h][0], kb_[2 * h][1]);
        mma0(n[4], n[5], n[6], n[7], e[0], e[1], e[2], e[3], kb_[2 * h][2], kb_[2 * h][3]);
        mma(dn[0], dn[1], dn[2], dn[3], e[4], e[5], e[6], e[7], zb[4 * h + 2], zb[4 * h + 3]);
        mma(n[0], n[1], n[2], n[3], e[4], e[5], e[6], e[7], kb_[2 * h + 1][0], kb_[2 * h + 1][1]);
        mma(n[4], n[5], n[6], n[7], e[4], e[5], e[6], e[7], kb_[2 * h + 1][2], kb_[2 * h + 1][3]);
        const float r0 = rcp(dn[0] + 1e-6f), r1 = rcp(dn[2] + 1e-6f);
        st_x(od + h * 128, nz(pack_bf(n[0] * r0, n[1] * r0)), pack_bf(n[2] * r1, n[3] * r1), pack_bf(n[4] * r0, n[5] * r0),
             pack_bf(n[6] * r1, n[7] * r1));
      }
#pragma unroll
      for (int i = 0; i < 16; i++) eq[i] = eq[16 + i];
      od += 4096;
    }
  }
  TS(wg * 16 + 7);
  const int rb = rt * 4 + (hp >> 2);
  const uint4* osrc = g_o + (size_t)(rb * 32 + wg * 16) * 128 + t;
  uint4 af[16];
  {
    const uint32_t* probe = (const uint32_t*)(osrc - lane + (lane & 15) * 128 + (lane >> 4) * 31);
#pragma unroll 1
    for (int it = 0; it < SPIN_MAX; it++) {
      uint32_t m = ld_x32(probe);
#pragma unroll
      for (int i = 0; i < 4; i++) af[i] = ld_x(osrc + i * 128);
#pragma unroll
      for (int i = 0; i < 4; i++) m = min(m, af[i].x);
      if (__all_sync(0xffffffffu, m != 0)) break;
    }
  }
#pragma unroll
  for (int i = 4; i < 16; i++) af[i] = ld_x(osrc + i * 128);
  TS(wg * 16 + 8);
  mbar_wait(BAR(MB_WO) + 8 * wg);
  nb_sync(NB_BDONE, 384);
  TS(wg * 16 + 9);
  float oc[64];
  {
    const uint64_t db = mkdesc(sb + OFF_W, 8192, 1024, 1) + wg * 4096;
#pragma unroll
    for (int j = 0; j < 4; j++) {
      if (j) {
#pragma unroll 1
        for (int it = 0; it < SPIN_MAX; it++) {
          const uint32_t m = min(min(af[4 * j].x, af[4 * j + 1].x), min(af[4 * j + 2].x, af[4 * j + 3].x));
          if (__all_sync(0xffffffffu, m != 0)) break;
#pragma unroll
          for (int i = 0; i < 4; i++) af[4 * j + i] = ld_x(osrc + (4 * j + i) * 128);
        }
      }
      WG_FENCE();
#pragma unroll
      for (int k = 0; k < 4; k++) wgmma_rs_n128(oc, af[4 * j + k], db + 128 * k + 1024 * j, j | k);
    }
    WG_COMMIT();
    WG_WAIT(0);
  }
  TS(wg * 16 + 10);
  const uint32_t xo = stg1 + wg * 16384 + t * 16, xi = stg1 + (wg ^ 1) * 16384 + t * 16;
#pragma unroll
  for (int i = 0; i < 8; i++) sts128(xo + i * 2048, fu(oc[32 + 4 * i]), fu(oc[33 + 4 * i]), fu(oc[34 + 4 * i]), fu(oc[35 + 4 * i]));
  nb_sync(NB_RED, 256);
  const uint32_t ot = stg0 + warp * 2048;
#pragma unroll
  for (int i = 0; i < 8; i += 2) {
    const uint4 v0 = lds128(xi + i * 2048), v1 = lds128(xi + i * 2048 + 2048);
    stsm4(ot + (lane & 15) * 128 + (((i + (lane >> 4)) ^ (lane & 7)) << 4),
          pack_bf(oc[4 * i] + uf(v0.x), oc[4 * i + 1] + uf(v0.y)), pack_bf(oc[4 * i + 2] + uf(v0.z), oc[4 * i + 3] + uf(v0.w)),
          pack_bf(oc[4 * i + 4] + uf(v1.x), oc[4 * i + 5] + uf(v1.y)), pack_bf(oc[4 * i + 6] + uf(v1.z), oc[4 * i + 7] + uf(v1.w)));
  }
  asm volatile("fence.proxy.async.shared::cta;" ::: "memory");
  __syncwarp();
  e_store2d(&mout, ot, (hp & 3) * 128 + wg * 64, rb * 64 + w * 16);
  TS(wg * 16 + 11);
  GT(61 + wg);
}

typedef CUresult (*EncodeFn)(CUtensorMap*, CUtensorMapDataType, cuuint32_t, void*, const cuuint64_t*, const cuuint64_t*,
                             const cuuint32_t*, const cuuint32_t*, CUtensorMapInterleave, CUtensorMapSwizzle,
                             CUtensorMapL2promotion, CUtensorMapFloatOOBfill);

}

extern "C" void kernel_launch(void* const* d_in, const int* in_sizes, int n_in, void* d_out, int out_size) {
  (void)in_sizes; (void)n_in; (void)out_size;
  void* fn = nullptr;
  cudaDriverEntryPointQueryResult qr;
  cudaGetDriverEntryPoint("cuTensorMapEncodeTiled", &fn, cudaEnableDefault, &qr);
  EncodeFn enc = (EncodeFn)fn;
  CUtensorMap mx, mw, mo, mu, mout;
  const cuuint32_t es[5] = {1, 1, 1, 1, 1};
  {
    cuuint64_t dims[2] = {512, 2048}, st[1] = {1024};
    cuuint32_t box[2] = {64, 128};
    enc(&mx, CU_TENSOR_MAP_DATA_TYPE_BFLOAT16, 2, d_in[0], dims, st, box, es, CU_TENSOR_MAP_INTERLEAVE_NONE,
        CU_TENSOR_MAP_SWIZZLE_128B, CU_TENSOR_MAP_L2_PROMOTION_L2_128B, CU_TENSOR_MAP_FLOAT_OOB_FILL_NONE);
  }
  {
    cuuint64_t dims[3] = {512, 512, 3}, st[2] = {3072, 1024};
    cuuint32_t box[3] = {32, 64, 3};
    enc(&mw, CU_TENSOR_MAP_DATA_TYPE_BFLOAT16, 3, d_in[1], dims, st, box, es, CU_TENSOR_MAP_INTERLEAVE_NONE,
        CU_TENSOR_MAP_SWIZZLE_64B, CU_TENSOR_MAP_L2_PROMOTION_L2_128B, CU_TENSOR_MAP_FLOAT_OOB_FILL_NONE);
  }
  {
    cuuint64_t dims[2] = {512, 512}, st[1] = {1024};
    cuuint32_t box[2] = {64, 64};
    enc(&mo, CU_TENSOR_MAP_DATA_TYPE_BFLOAT16, 2, d_in[3], dims, st, box, es, CU_TENSOR_MAP_INTERLEAVE_NONE,
        CU_TENSOR_MAP_SWIZZLE_128B, CU_TENSOR_MAP_L2_PROMOTION_L2_128B, CU_TENSOR_MAP_FLOAT_OOB_FILL_NONE);
  }
  {
    cuuint64_t dims[5] = {512, 2, 4, 4, 64}, st[4] = {1024, 8192, 2048, 32768};
    cuuint32_t box[5] = {64, 2, 4, 4, 4};
    enc(&mu, CU_TENSOR_MAP_DATA_TYPE_BFLOAT16, 5, d_in[4], dims, st, box, es, CU_TENSOR_MAP_INTERLEAVE_NONE,
        CU_TENSOR_MAP_SWIZZLE_128B, CU_TENSOR_MAP_L2_PROMOTION_L2_128B, CU_TENSOR_MAP_FLOAT_OOB_FILL_NONE);
  }
  {
    cuuint64_t dims[2] = {1024, 2048}, st[1] = {2048};
    cuuint32_t box[2] = {64, 16};
    enc(&mout, CU_TENSOR_MAP_DATA_TYPE_BFLOAT16, 2, d_out, dims, st, box, es, CU_TENSOR_MAP_INTERLEAVE_NONE,
        CU_TENSOR_MAP_SWIZZLE_128B, CU_TENSOR_MAP_L2_PROMOTION_NONE, CU_TENSOR_MAP_FLOAT_OOB_FILL_NONE);
  }
  Params P;
  P.x = (const __nv_bfloat16*)d_in[0];
  P.wphi = (const __nv_bfloat16*)d_in[2];
  P.wo = (const __nv_bfloat16*)d_in[3];
  P.u = (const __nv_bfloat16*)d_in[4];
  P.logA = (const __nv_bfloat16*)d_in[5];
  P.Aim = (const __nv_bfloat16*)d_in[6];
  P.Cre = (const __nv_bfloat16*)d_in[7];
  P.Cim = (const __nv_bfloat16*)d_in[8];
  P.logdt = (const __nv_bfloat16*)d_in[9];
  P.Dskip = (const __nv_bfloat16*)d_in[10];
  P.out = (__nv_bfloat16*)d_out;
  cudaFuncSetAttribute(fused_kernel, cudaFuncAttributeMaxDynamicSharedMemorySize, SMEM_BYTES);
  fused_kernel<<<NCTA, NTHREADS, SMEM_BYTES>>>(P, mx, mw, mo, mu, mout);
}
```

```cpp
#include <cuda_runtime.h>
#include <cuda_bf16.h>
#include <cuda_fp16.h>
#include <cuda.h>
#include <stdint.h>

#define DBG_TS 0

namespace {

constexpr int NTHREADS = 512;
constexpr int NCTA = 128;
constexpr int OFF_W = 0;
constexpr int OFF_X = 98304;
constexpr int OFF_U = OFF_X + 65536;
constexpr int U_CH = 4416, U_ODD = 2240, U_PAD = 128;
constexpr int OFF_STG0 = OFF_U + 18432;
constexpr int OFF_T = OFF_STG0 + 24576;
constexpr int T_CH = 5216;
constexpr int T_D = 0;
constexpr int T_5 = 2144;
constexpr int T_3 = T_5 + 384;
constexpr int T_7 = T_5 + 1024;
constexpr int T_9 = T_7 + 320;
constexpr int T_KC = T_9 + 320;
constexpr int T_ST = T_5 - 1024;
constexpr int OFF_PHI = OFF_T + 4 * T_CH;
constexpr int OFF_BAR = OFF_PHI + 1024;
constexpr int SMEM_BYTES = OFF_BAR + 512;
constexpr uint32_t SB = 1024;
static_assert(T_KC + 2 * 656 <= T_CH, "table size");
static_assert(SMEM_BYTES <= 232448, "smem");
constexpr int MB_URAW = 0, MB_FULL = 1  , MB_WO = 17  , MB_UFULL = 19,
              MB_EMPTY = 21  , MB_CLOSE = 37;
__host__ __device__ constexpr uint32_t BAR(int i) { return SB + OFF_BAR + 8 * i; }
constexpr int NB_WG0 = 1, NB_KPART = 2, NB_ST0 = 3  , NB_KV = 5, NB_RED = 6, NB_INIT = 7, NB_PREP = 8, NB_PROD = 9, NB_RDY = 10, NB_BDONE = 11, NB_ZERO = 12;
#define ZERO_N 1024
#define ZERO_STEP 0
#define STEPU 0
#define STEPPF 0
constexpr int STEP_PF = STEPPF, STEP_U = STEPU;
constexpr int SPIN_MAX = 1 << 16;

constexpr int X_CNT = 0;
constexpr int X_PART = 8;
constexpr int X_O = X_PART + 16 * 8 * 144;
constexpr int X_Y = X_O + 32 * 32 * 128;
constexpr int X_UT = X_Y + 512 * 8 * 32;
constexpr int X_SIZE = X_UT + 512 * 256;
__device__ __align__(128) uint4 g_x[X_SIZE];
extern __shared__ uint8_t smem_raw[];
#define TS(i) do {} while (0)
#define TS1(i) do {} while (0)
#define GT(i) do {} while (0)

__device__ __forceinline__ uint32_t smem_u32(const void* p) { return (uint32_t)__cvta_generic_to_shared(p); }
__device__ __forceinline__ void mbar_arrive(uint32_t b) {
  asm volatile("mbarrier.arrive.shared::cta.b64 _, [%0];" ::"r"(b) : "memory");
}
__device__ __forceinline__ void mbar_wait(uint32_t b) {
  uint32_t done = 0;
#pragma unroll 1
  for (int i = 0; i < SPIN_MAX && !done; i++) {
    asm volatile("{\n.reg .pred p;\nmbarrier.try_wait.parity.shared::cta.b64 p, [%1], 0, 4000;\nselp.u32 %0, 1, 0, p;\n}\n"
                 : "=r"(done) : "r"(b) : "memory");
  }
}
__device__ __forceinline__ void mbar_init(uint32_t b, int n) {
  asm volatile("mbarrier.init.shared::cta.b64 [%0], %1;" ::"r"(b), "r"(n) : "memory");
}
__device__ __forceinline__ void mbar_expect(uint32_t b, int bytes) {
  asm volatile("mbarrier.arrive.expect_tx.shared::cta.b64 _, [%0], %1;" ::"r"(b), "r"(bytes) : "memory");
}
__device__ __forceinline__ void nb_sync(int id, int n) { asm volatile("bar.sync %0, %1;" ::"r"(id), "r"(n) : "memory"); }
__device__ __forceinline__ void nb_arrive(int id, int n) { asm volatile("bar.arrive %0, %1;" ::"r"(id), "r"(n) : "memory"); }
#define ELECT "{\n.reg .pred p;\nelect.sync _|p, 0xffffffff;\n@p "
__device__ __forceinline__ void e_expect(uint32_t b, int bytes) {
  asm volatile(ELECT "mbarrier.arrive.expect_tx.shared::cta.b64 _, [%0], %1;\n}\n" ::"r"(b), "r"(bytes) : "memory");
}
__device__ __forceinline__ void e_tma2d(uint32_t dst, const CUtensorMap* m, uint32_t bar, int c0, int c1) {
  asm volatile(ELECT "cp.async.bulk.tensor.2d.shared::cluster.global.mbarrier::complete_tx::bytes [%0], [%1, {%3,%4}], [%2];\n}\n"
               ::"r"(dst), "l"(m), "r"(bar), "r"(c0), "r"(c1) : "memory");
}
__device__ __forceinline__ void e_tma3d(uint32_t dst, const CUtensorMap* m, uint32_t bar, int c0, int c1, int c2) {
  asm volatile(ELECT "cp.async.bulk.tensor.3d.shared::cluster.global.mbarrier::complete_tx::bytes [%0], [%1, {%3,%4,%5}], [%2];\n}\n"
               ::"r"(dst), "l"(m), "r"(bar), "r"(c0), "r"(c1), "r"(c2) : "memory");
}
__device__ __forceinline__ void e_tma5d(uint32_t dst, const CUtensorMap* m, uint32_t bar, int c0, int c4) {
  asm volatile(ELECT "cp.async.bulk.tensor.5d.shared::cluster.global.mbarrier::complete_tx::bytes [%0], [%1, {%3,%5,%5,%5,%4}], [%2];\n}\n"
               ::"r"(dst), "l"(m), "r"(bar), "r"(c0), "r"(c4), "r"(0) : "memory");
}
__device__ __forceinline__ void e_bulk(uint32_t dst, const void* src, int bytes, uint32_t bar) {
  asm volatile(ELECT "cp.async.bulk.shared::cluster.global.mbarrier::complete_tx::bytes [%0], [%1], %2, [%3];\n}\n"
               ::"r"(dst), "l"(src), "r"(bytes), "r"(bar) : "memory");
}
__device__ __forceinline__ void e_prefetch(const void* p, int bytes) {
  asm volatile(ELECT "cp.async.bulk.prefetch.L2.global [%0], %1;\n}\n" ::"l"(p), "r"(bytes) : "memory");
}
__device__ __forceinline__ void e_store2d(const CUtensorMap* m, uint32_t src, int c0, int c1) {
  asm volatile(ELECT "cp.async.bulk.tensor.2d.global.shared::cta.bulk_group [%0, {%2,%3}], [%1];\n"
               "@p cp.async.bulk.commit_group;\n@p cp.async.bulk.wait_group.read 0;\n}\n"
               ::"l"(m), "r"(src), "r"(c0), "r"(c1) : "memory");
}
__host__ __device__ constexpr uint64_t mkdesc(uint32_t addr, uint32_t lbo, uint32_t sbo, int swz) {
  return (uint64_t)((addr & 0x3FFFF) >> 4) | ((uint64_t)(lbo >> 4) << 16) | ((uint64_t)(sbo >> 4) << 32) |
         ((uint64_t)swz << 62);
}
#define WG_FENCE() asm volatile("wgmma.fence.sync.aligned;" ::: "memory")
#define WG_COMMIT() asm volatile("wgmma.commit_group.sync.aligned;" ::: "memory")
#define WG_WAIT(n) asm volatile("wgmma.wait_group.sync.aligned " #n ";" ::: "memory")

__device__ __forceinline__ void mma(float& d0, float& d1, float& d2, float& d3, uint32_t a0, uint32_t a1, uint32_t a2,
                                    uint32_t a3, uint32_t b0, uint32_t b1) {
  asm volatile("mma.sync.aligned.m16n8k16.row.col.f32.bf16.bf16.f32 {%0,%1,%2,%3},{%4,%5,%6,%7},{%8,%9},{%0,%1,%2,%3};"
               : "+f"(d0), "+f"(d1), "+f"(d2), "+f"(d3)
               : "r"(a0), "r"(a1), "r"(a2), "r"(a3), "r"(b0), "r"(b1));
}
__device__ __forceinline__ void mmac(float (&d)[4], uint32_t a0, uint32_t a1, uint32_t a2, uint32_t a3, uint32_t b0,
                                     uint32_t b1, const float (&c)[4]) {
  asm volatile("mma.sync.aligned.m16n8k16.row.col.f32.bf16.bf16.f32 {%0,%1,%2,%3},{%4,%5,%6,%7},{%8,%9},{%10,%11,%12,%13};"
               : "=f"(d[0]), "=f"(d[1]), "=f"(d[2]), "=f"(d[3])
               : "r"(a0), "r"(a1), "r"(a2), "r"(a3), "r"(b0), "r"(b1), "f"(c[0]), "f"(c[1]), "f"(c[2]), "f"(c[3]));
}
__device__ __forceinline__ void mma_p(int p, float (&d)[4], uint32_t a0, uint32_t a1, uint32_t a2, uint32_t a3, uint32_t b0, uint32_t b1) {
  asm volatile("{\n.reg .pred q;\nsetp.ne.b32 q, %10, 0;\n"
               "@q mma.sync.aligned.m16n8k16.row.col.f32.bf16.bf16.f32 {%0,%1,%2,%3},{%4,%5,%6,%7},{%8,%9},{%0,%1,%2,%3};\n}\n"
               : "+f"(d[0]), "+f"(d[1]), "+f"(d[2]), "+f"(d[3])
               : "r"(a0), "r"(a1), "r"(a2), "r"(a3), "r"(b0), "r"(b1), "r"(p));
}
__device__ __forceinline__ void mmac_p(int p, float (&d)[4], uint32_t a0, uint32_t a1, uint32_t a2, uint32_t a3, uint32_t b0,
                                       uint32_t b1, const float (&c)[4]) {
  asm volatile("{\n.reg .pred q;\nsetp.ne.b32 q, %14, 0;\n"
               "@q mma.sync.aligned.m16n8k16.row.col.f32.bf16.bf16.f32 {%0,%1,%2,%3},{%4,%5,%6,%7},{%8,%9},{%10,%11,%12,%13};\n}\n"
               : "+f"(d[0]), "+f"(d[1]), "+f"(d[2]), "+f"(d[3])
               : "r"(a0), "r"(a1), "r"(a2), "r"(a3), "r"(b0), "r"(b1), "f"(c[0]), "f"(c[1]), "f"(c[2]), "f"(c[3]), "r"(p));
}
__device__ __forceinline__ void mma_k8(float (&d)[4], uint32_t a0, uint32_t a1, uint32_t b0) {
  asm volatile("mma.sync.aligned.m16n8k8.row.col.f32.bf16.bf16.f32 {%0,%1,%2,%3},{%4,%5},{%6},{%0,%1,%2,%3};"
               : "+f"(d[0]), "+f"(d[1]), "+f"(d[2]), "+f"(d[3]) : "r"(a0), "r"(a1), "r"(b0));
}
__device__ __forceinline__ void mma0(float& d0, float& d1, float& d2, float& d3, uint32_t a0, uint32_t a1, uint32_t a2,
                                     uint32_t a3, uint32_t b0, uint32_t b1) {
  asm volatile("mma.sync.aligned.m16n8k16.row.col.f32.bf16.bf16.f32 {%0,%1,%2,%3},{%4,%5,%6,%7},{%8,%9},{%10,%10,%10,%10};"
               : "=f"(d0), "=f"(d1), "=f"(d2), "=f"(d3)
               : "r"(a0), "r"(a1), "r"(a2), "r"(a3), "r"(b0), "r"(b1), "f"(0.f));
}
__device__ __forceinline__ uint32_t pack_bf(float lo, float hi) {
  uint32_t r;
  asm("cvt.rn.bf16x2.f32 %0, %1, %2;" : "=r"(r) : "f"(hi), "f"(lo));
  return r;
}
__device__ __forceinline__ float bf_lo(uint32_t w) { return __uint_as_float(w << 16); }
__device__ __forceinline__ float bf_hi(uint32_t w) { return __uint_as_float(w & 0xffff0000u); }
__device__ __forceinline__ float bf_round(float x) { return __bfloat162float(__float2bfloat16_rn(x)); }
__device__ __forceinline__ uint32_t bmax2(uint32_t a, uint32_t b) {
  uint32_t r; asm("max.bf16x2 %0, %1, %2;" : "=r"(r) : "r"(a), "r"(b)); return r;
}
__device__ __forceinline__ uint32_t bmin2(uint32_t a, uint32_t b) {
  uint32_t r; asm("min.bf16x2 %0, %1, %2;" : "=r"(r) : "r"(a), "r"(b)); return r;
}
__device__ __forceinline__ float ex2(float x) { float r; asm("ex2.approx.ftz.f32 %0, %1;" : "=f"(r) : "f"(x)); return r; }
__device__ __forceinline__ float rcp(float x) { float r; asm("rcp.approx.ftz.f32 %0, %1;" : "=f"(r) : "f"(x)); return r; }
__device__ __forceinline__ void ldsm4(uint32_t (&r)[4], uint32_t a) {
  asm volatile("ldmatrix.sync.aligned.m8n8.x4.shared.b16 {%0,%1,%2,%3}, [%4];"
               : "=r"(r[0]), "=r"(r[1]), "=r"(r[2]), "=r"(r[3]) : "r"(a) : "memory");
}
__device__ __forceinline__ void ldsm4t(uint32_t (&r)[4], uint32_t a) {
  asm volatile("ldmatrix.sync.aligned.m8n8.x4.trans.shared.b16 {%0,%1,%2,%3}, [%4];"
               : "=r"(r[0]), "=r"(r[1]), "=r"(r[2]), "=r"(r[3]) : "r"(a) : "memory");
}
__device__ __forceinline__ void stsm4(uint32_t a, uint32_t r0, uint32_t r1, uint32_t r2, uint32_t r3) {
  asm volatile("stmatrix.sync.aligned.m8n8.x4.shared.b16 [%0], {%1,%2,%3,%4};"
               ::"r"(a), "r"(r0), "r"(r1), "r"(r2), "r"(r3) : "memory");
}
__device__ __forceinline__ uint32_t lds32(uint32_t a) {
  uint32_t r; asm volatile("ld.shared.u32 %0, [%1];" : "=r"(r) : "r"(a) : "memory"); return r;
}
__device__ __forceinline__ uint32_t lds16(uint32_t a) {
  uint32_t r; asm volatile("{\n.reg .u16 h;\nld.shared.u16 h, [%1];\ncvt.u32.u16 %0, h;\n}\n" : "=r"(r) : "r"(a) : "memory"); return r;
}
__device__ __forceinline__ uint2 lds64(uint32_t a) {
  uint2 r; asm volatile("ld.shared.v2.u32 {%0,%1}, [%2];" : "=r"(r.x), "=r"(r.y) : "r"(a) : "memory"); return r;
}
__device__ __forceinline__ uint4 lds128(uint32_t a) {
  uint4 r;
  asm volatile("ld.shared.v4.u32 {%0,%1,%2,%3}, [%4];" : "=r"(r.x), "=r"(r.y), "=r"(r.z), "=r"(r.w) : "r"(a) : "memory");
  return r;
}
__device__ __forceinline__ void sts32(uint32_t a, uint32_t v) { asm volatile("st.shared.u32 [%0], %1;" ::"r"(a), "r"(v) : "memory"); }
__device__ __forceinline__ void sts16(uint32_t a, uint32_t v) {
  asm volatile("{\n.reg .u16 h;\ncvt.u16.u32 h, %1;\nst.shared.u16 [%0], h;\n}\n" ::"r"(a), "r"(v) : "memory");
}
__device__ __forceinline__ void sts64(uint32_t a, uint32_t x, uint32_t y) {
  asm volatile("st.shared.v2.u32 [%0], {%1,%2};" ::"r"(a), "r"(x), "r"(y) : "memory");
}
__device__ __forceinline__ void sts128(uint32_t a, uint32_t x, uint32_t y, uint32_t z, uint32_t w) {
  asm volatile("st.shared.v4.u32 [%0], {%1,%2,%3,%4};" ::"r"(a), "r"(x), "r"(y), "r"(z), "r"(w) : "memory");
}
__device__ __forceinline__ uint4 ld_x(const uint4* p) {
  uint4 r;
  asm volatile("{\n.reg .b128 t;\nld.relaxed.gpu.global.b128 t, [%4];\nmov.b128 {%0,%1,%2,%3}, t;\n}\n"
               : "=r"(r.x), "=r"(r.y), "=r"(r.z), "=r"(r.w) : "l"(p) : "memory");
  return r;
}
__device__ __forceinline__ uint32_t ld_x32(const uint32_t* p) {
  uint32_t r; asm volatile("ld.relaxed.gpu.global.u32 %0, [%1];" : "=r"(r) : "l"(p) : "memory"); return r;
}
__device__ __forceinline__ void st_x(uint4* p, uint32_t x, uint32_t y, uint32_t z, uint32_t w) {
  asm volatile("{\n.reg .b128 t;\nmov.b128 t, {%1,%2,%3,%4};\nst.relaxed.gpu.global.b128 [%0], t;\n}\n"
               ::"l"(p), "r"(x), "r"(y), "r"(z), "r"(w) : "memory");
}
__device__ __forceinline__ void st_x_p(int p, uint4* a, uint32_t x, uint32_t y, uint32_t z, uint32_t w) {
  asm volatile("{\n.reg .b128 t;\n.reg .pred q;\nsetp.ne.b32 q, %5, 0;\nmov.b128 t, {%1,%2,%3,%4};\n@q st.relaxed.gpu.global.b128 [%0], t;\n}\n"
               ::"l"(a), "r"(x), "r"(y), "r"(z), "r"(w), "r"(p) : "memory");
}
__device__ __forceinline__ void sts64_p(int p, uint32_t a, uint32_t x, uint32_t y) {
  asm volatile("{\n.reg .pred q;\nsetp.ne.b32 q, %3, 0;\n@q st.shared.v2.u32 [%0], {%1,%2};\n}\n" ::"r"(a), "r"(x), "r"(y), "r"(p) : "memory");
}
__device__ __forceinline__ void st_x32(uint32_t* p, uint32_t x) {
  asm volatile("st.relaxed.gpu.global.u32 [%0], %1;" ::"l"(p), "r"(x) : "memory");
}
__device__ __forceinline__ uint32_t nz(uint32_t w) { return max(w, 1u); }
__device__ __forceinline__ uint32_t fu(float x) { return __float_as_uint(x); }
__device__ __forceinline__ float uf(uint32_t x) { return __uint_as_float(x); }

__device__ __forceinline__ void wgmma_ss_n96(float (&d)[48], uint64_t da, uint64_t db, int sc) {
  asm volatile("{\n.reg .pred p;\nsetp.ne.b32 p, %50, 0;\n"
      "wgmma.mma_async.sync.aligned.m64n96k16.f32.bf16.bf16 "
      "{%0,%1,%2,%3,%4,%5,%6,%7,%8,%9,%10,%11,%12,%13,%14,%15,%16,%17,%18,%19,%20,%21,%22,%23,%24,%25,%26,%27,%28,%29,%30,%31,%32,%33,%34,%35,%36,%37,%38,%39,%40,%41,%42,%43,%44,%45,%46,%47}, "
      "%48, %49, p, 1, 1, 0, 1;\n}\n"
      : "+f"(d[0]), "+f"(d[1]), "+f"(d[2]), "+f"(d[3]), "+f"(d[4]), "+f"(d[5]), "+f"(d[6]), "+f"(d[7]),
        "+f"(d[8]), "+f"(d[9]), "+f"(d[10]), "+f"(d[11]), "+f"(d[12]), "+f"(d[13]), "+f"(d[14]), "+f"(d[15]),
        "+f"(d[16]), "+f"(d[17]), "+f"(d[18]), "+f"(d[19]), "+f"(d[20]), "+f"(d[21]), "+f"(d[22]), "+f"(d[23]),
        "+f"(d[24]), "+f"(d[25]), "+f"(d[26]), "+f"(d[27]), "+f"(d[28]), "+f"(d[29]), "+f"(d[30]), "+f"(d[31]),
        "+f"(d[32]), "+f"(d[33]), "+f"(d[34]), "+f"(d[35]), "+f"(d[36]), "+f"(d[37]), "+f"(d[38]), "+f"(d[39]),
        "+f"(d[40]), "+f"(d[41]), "+f"(d[42]), "+f"(d[43]), "+f"(d[44]), "+f"(d[45]), "+f"(d[46]), "+f"(d[47])
      : "l"(da), "l"(db), "r"(sc));
}

__device__ __forceinline__ void wgmma_rs_n128(float (&d)[64], const uint4& a, uint64_t db, int sc) {
  asm volatile("{\n.reg .pred p;\nsetp.ne.b32 p, %69, 0;\n"
      "wgmma.mma_async.sync.aligned.m64n128k16.f32.bf16.bf16 "
      "{%0,%1,%2,%3,%4,%5,%6,%7,%8,%9,%10,%11,%12,%13,%14,%15,%16,%17,%18,%19,%20,%21,%22,%23,%24,%25,%26,%27,%28,%29,%30,%31,%32,%33,%34,%35,%36,%37,%38,%39,%40,%41,%42,%43,%44,%45,%46,%47,%48,%49,%50,%51,%52,%53,%54,%55,%56,%57,%58,%59,%60,%61,%62,%63}, "
      "{%64,%65,%66,%67}, %68, p, 1, 1, 1;\n}\n"
      : "+f"(d[0]), "+f"(d[1]), "+f"(d[2]), "+f"(d[3]), "+f"(d[4]), "+f"(d[5]), "+f"(d[6]), "+f"(d[7]),
        "+f"(d[8]), "+f"(d[9]), "+f"(d[10]), "+f"(d[11]), "+f"(d[12]), "+f"(d[13]), "+f"(d[14]), "+f"(d[15]),
        "+f"(d[16]), "+f"(d[17]), "+f"(d[18]), "+f"(d[19]), "+f"(d[20]), "+f"(d[21]), "+f"(d[22]), "+f"(d[23]),
        "+f"(d[24]), "+f"(d[25]), "+f"(d[26]), "+f"(d[27]), "+f"(d[28]), "+f"(d[29]), "+f"(d[30]), "+f"(d[31]),
        "+f"(d[32]), "+f"(d[33]), "+f"(d[34]), "+f"(d[35]), "+f"(d[36]), "+f"(d[37]), "+f"(d[38]), "+f"(d[39]),
        "+f"(d[40]), "+f"(d[41]), "+f"(d[42]), "+f"(d[43]), "+f"(d[44]), "+f"(d[45]), "+f"(d[46]), "+f"(d[47]),
        "+f"(d[48]), "+f"(d[49]), "+f"(d[50]), "+f"(d[51]), "+f"(d[52]), "+f"(d[53]), "+f"(d[54]), "+f"(d[55]),
        "+f"(d[56]), "+f"(d[57]), "+f"(d[58]), "+f"(d[59]), "+f"(d[60]), "+f"(d[61]), "+f"(d[62]), "+f"(d[63])
      : "r"(a.x), "r"(a.y), "r"(a.z), "r"(a.w), "l"(db), "r"(sc));
}

struct Params {
  const __nv_bfloat16 *logA, *Aim, *Cre, *Cim, *logdt, *Dskip, *x, *wphi, *wo;
  __nv_bfloat16* out;
  uint4* xs;
  long long* ts;
};

__device__ __forceinline__ uint4 tr_row(const uint4 (&v)[8], int i) {
  uint32_t o[4];
#pragma unroll
  for (int m = 0; m < 4; m++) {
    const uint4 &ra = v[2 * m], &rb = v[2 * m + 1];
    const int k = i >> 1;
    const uint32_t xa = k == 0 ? ra.x : k == 1 ? ra.y : k == 2 ? ra.z : ra.w;
    const uint32_t xb = k == 0 ? rb.x : k == 1 ? rb.y : k == 2 ? rb.z : rb.w;
    o[m] = __byte_perm(xa, xb, (i & 1) ? 0x7632 : 0x5410);
  }
  return make_uint4(o[0], o[1], o[2], o[3]);
}

struct cpx { float r, i; };
__device__ __forceinline__ cpx cmul(cpx a, cpx b) { return {a.r * b.r - a.i * b.i, a.r * b.i + a.i * b.r}; }
__device__ __forceinline__ cpx csq(cpx a) { return {a.r * a.r - a.i * a.i, 2.f * (a.r * a.i)}; }
__device__ __forceinline__ cpx polar(float e, float t) {
  const float m = ex2(e);
  return {m * __cosf(t), m * __sinf(t)};
}

struct KgenRaw { unsigned short la, ai, cr, ci, ldt; };
__device__ __forceinline__ KgenRaw kgen_load(const Params& P, int d, int unit, int lane) {
  const int o = d * 128 + unit * 32 + lane;
  return {__ldg((const unsigned short*)P.logA + o), __ldg((const unsigned short*)P.Aim + o), __ldg((const unsigned short*)P.Cre + o),
          __ldg((const unsigned short*)P.Cim + o), __ldg((const unsigned short*)P.logdt + d)};
}
__device__ __forceinline__ void kgen_unit(const KgenRaw& r, int lane, uint32_t buf, uint32_t open_bar, float& dt,
                                          float (&k)[5][4], float& k2048) {
  dt = bf_round(expf(bf_lo(r.ldt)));
  const float a2 = -(bf_round(expf(bf_lo(r.la))) * dt) * 1.4426950408889634f;
  const float f = bf_lo(r.ai) * dt;
  const float r128 = f * 20.371832715762604f;
  const cpx C = {bf_lo(r.cr), -bf_lo(r.ci)};
  const uint32_t sa = buf + (lane & 7) * 128 + ((((lane >> 3) ^ lane) & 7) << 4);
  const uint32_t lb = buf + (lane >> 3) * 128 + (((lane ^ (lane >> 3)) & 7) << 4);
  const uint32_t la = buf + ((lane >> 3) & 1) * 1024 + (lane >> 4) * 128 + (((lane ^ (lane >> 4)) & 7) << 4);
  auto put = [&](const cpx (&v)[8], uint32_t off) {
    stsm4(sa + off, pack_bf(v[0].r, v[0].i), pack_bf(v[1].r, v[1].i), pack_bf(v[2].r, v[2].i), pack_bf(v[3].r, v[3].i));
    stsm4((sa ^ 64) + off, pack_bf(v[4].r, v[4].i), pack_bf(v[5].r, v[5].i), pack_bf(v[6].r, v[6].i), pack_bf(v[7].r, v[7].i));
  };
  uint32_t A[4][4], B[5][2][4];
  auto getB = [&](int j, uint32_t off) {
    __syncwarp();
    ldsm4(B[j][0], lb + off);
    ldsm4(B[j][1], (lb ^ 64) + 512 + off);
  };
  cpx t0[8], t1[8], t2[8], t3[8], t4[8];
  t0[0] = {1.f, 0.f};
  t0[1] = polar(a2, f);
  t1[0] = polar(a2 * 128.f, (r128 - rintf(r128)) * 6.283185307179586f);
  t0[2] = csq(t0[1]); t0[4] = csq(t0[2]);
  t2[0] = csq(t1[0]); t3[0] = csq(t2[0]); t4[0] = csq(t3[0]);
  t0[3] = cmul(t0[2], t0[1]); t0[5] = cmul(t0[4], t0[1]); t0[6] = cmul(t0[4], t0[2]); t0[7] = cmul(t0[4], t0[3]);
  put(t0, 0); getB(0, 0);
  {
    cpx w8 = csq(t0[4]);
    w8.i = -w8.i;
    const cpx w16 = csq(w8), w32 = csq(w16), w64 = csq(w32);
    cpx a[8];
    a[0] = C; a[1] = cmul(C, w8);
    a[2] = cmul(a[0], w16); a[3] = cmul(a[1], w16);
#pragma unroll
    for (int i = 0; i < 4; i++) a[4 + i] = cmul(a[i], w32);
    put(a, 0);
#pragma unroll
    for (int i = 0; i < 8; i++) a[i] = cmul(a[i], w64);
    put(a, 1024);
    __syncwarp();
#pragma unroll
    for (int s = 0; s < 4; s++) ldsm4(A[s], (la ^ (s << 5)) + s * 256);
  }
#pragma unroll
  for (int i = 1; i < 8; i++) t1[i] = cmul(t0[i], t1[0]);
  put(t1, 0); getB(1, 0);
#pragma unroll
  for (int i = 1; i < 8; i++) t2[i] = cmul((i & 1) ? t1[i & 6] : t0[i & 6], t2[0]);
  put(t2, 1024); getB(2, 1024);
#pragma unroll
  for (int i = 1; i < 8; i++) t3[i] = cmul((i & 2) ? t2[i & 5] : ((i & 1) ? t1[i & 4] : t0[i & 4]), t3[0]);
  put(t3, 0); getB(3, 0);
#pragma unroll
  for (int i = 1; i < 8; i++) t4[i] = cmul((i & 4) ? t3[i & 3] : ((i & 2) ? t2[i & 1] : t1[0]), t4[0]);
  put(t4, 1024); getB(4, 1024);
  const cpx we = csq(t4[0]);
  k2048 += C.r * we.r + C.i * we.i;
  if (open_bar) mbar_wait(open_bar);
#pragma unroll
  for (int s = 0; s < 4; s++)
#pragma unroll
    for (int j = 0; j < 5; j++)
      mma(k[j][0], k[j][1], k[j][2], k[j][3], A[s][0], A[s][1], A[s][2], A[s][3], B[j][s >> 1][2 * (s & 1)], B[j][s >> 1][2 * (s & 1) + 1]);
}

__device__ __forceinline__ void build_tables(uint32_t tb, int lane, float (&k)[5][4], float k2048) {
  const int g = lane >> 2, c = lane & 3;
  const uint32_t kc = tb + T_KC + 16;
  {
    const uint32_t a0 = kc + 16 * g + 4 * c, a2 = kc + 2 * (256 + 4 * g + c);
    const uint32_t a3 = kc + 2 * (384 + 2 * g + 64 * (c & 1) + (c >> 1)), a4 = kc + 2 * (512 + g + 32 * c);
#pragma unroll
    for (int r = 0; r < 2; r++) {
      sts32(a0 + 128 * r, pack_bf(k[0][2 * r], k[0][2 * r + 1]));
      sts32(a0 + 128 * r + 256, pack_bf(k[1][2 * r], k[1][2 * r + 1]));
      const uint32_t w2 = pack_bf(k[2][2 * r], k[2][2 * r + 1]);
      const uint32_t w3 = pack_bf(k[3][2 * r], k[3][2 * r + 1]);
      const uint32_t w4 = pack_bf(k[4][2 * r], k[4][2 * r + 1]);
      sts16(a2 + 64 * r, w2); sts16(a2 + 64 * r + 128, w2 >> 16);
      sts16(a3 + 32 * r, w3); sts16(a3 + 32 * r + 64, w3 >> 16);
      sts16(a4 + 16 * r, w4); sts16(a4 + 16 * r + 32, w4 >> 16);
    }
  }
  if (lane == 0) { sts16(kc + 2 * 640, pack_bf(k2048, 0.f)); sts16(kc - 2, 0); }
  __syncwarp();
  const uint32_t td = tb + T_D + 32;
  {
    const uint4 v = lds128(kc + 16 * lane);
    const uint32_t pv = lds16(kc + 16 * lane - 2);
    sts128(td + 32 * lane, __byte_perm(v.x, pv, 0x5410), __byte_perm(v.x, v.x, 0x1032), __byte_perm(v.y, v.x, 0x7610),
           __byte_perm(v.y, v.y, 0x1032));
    sts128(td + 32 * lane + 16, __byte_perm(v.z, v.y, 0x7610), __byte_perm(v.z, v.z, 0x1032),
           __byte_perm(v.w, v.z, 0x7610), __byte_perm(v.w, v.w, 0x1032));
  }
  {
    const uint2 v = lds64(kc + 512 + 8 * lane);
    const uint32_t k4 = lds16(kc + 512 + 8 * lane + 8);
    const uint32_t pv = lds16(kc + (lane == 0 ? 510 : 512 + 8 * lane));
    const uint32_t k22 = __byte_perm(v.y, v.y, 0x1010);
    sts128(td + 1024 + 32 * lane, __byte_perm(v.x, pv, 0x5410), __byte_perm(v.x, v.x, 0x1010),
           __byte_perm(v.x, v.x, 0x1032), __byte_perm(v.y, v.x, 0x7610));
    sts128(td + 1024 + 32 * lane + 16, k22, k22, __byte_perm(v.y, v.y, 0x1032), __byte_perm(k4, v.y, 0x7610));
  }
  {
    const uint32_t kk = lds16(kc + 2 * 384);
    const uint32_t w = lane < 3 ? (kk | (kk << 16)) : (lane == 3 ? (kk << 16) : 0u);
    if (lane < 24) sts32(td + 4 * (lane < 16 ? 512 + lane : lane - 24), w);
    const uint32_t lo_ = lds16(kc + 2 * 511), le_ = lds16(kc + 2 * 512);
    const uint32_t ja = tb + T_5 + (lane < 16 ? 4 * lane : 256 + 4 * lane);
    sts32(ja, lane == 16 ? (le_ << 16) : 0u);
    sts32(ja + 384, lane == 16 ? (lo_ << 16) : 0u);
    sts32(tb + (lane < 16 ? T_7 : T_9 - 64) + 4 * lane, 0u);
  }
#pragma unroll
  for (int s = 0; s < 2; s++) {
    const uint32_t b = kc + 2 * (s ? 512 : 384) + 8 * lane;
    const uint2 v = lds64(b);
    uint32_t em = lds16(b - 2), e0 = v.x;
    const uint32_t e4 = lds16(b + 8);
    if (lane == 0) { em = 0; e0 = 0; }
    sts64(tb + (s ? T_7 : T_3) + 64 + 8 * lane, __byte_perm(v.x, em, 0x5432), __byte_perm(v.y, v.x, 0x7632));
    sts64(tb + (s ? T_9 : T_5) + 64 + 8 * lane, __byte_perm(v.y, e0, 0x5410), __byte_perm(e4, v.y, 0x5410));
  }
  __syncwarp();
}

__device__ __forceinline__ uint32_t box2w(int lo, int n, int o) {
  return ((unsigned)(o - lo) < (unsigned)n ? 0x3F80u : 0u) | ((unsigned)(o + 1 - lo) < (unsigned)n ? 0x3F800000u : 0u);
}

__device__ __forceinline__ void conv_channel(uint32_t ub, uint32_t tb, int lane, uint4* ydst) {
  const int g = lane >> 2, c = lane & 3, x = g - 2 * c;
  const uint32_t st = tb + T_ST + lane * 8;
  const int mi = lane >> 3;
  const uint32_t qa = ub + U_PAD + 16 * (lane & 7) + ((mi == 0 || mi == 3) ? U_ODD : 0) - (mi == 0 ? 16 : 0);
  const uint32_t kv = lds16(tb + T_KC + 16 + 2 * 512);
  {
    const uint32_t hb = ub + U_PAD + (mi & 1) * U_ODD + 16 * ((lane >> 4) + (lane & 7)) - 16;
    const int oh = c < 2 ? 8 + 2 * c : 2 * c - 8;
    const uint32_t bx0 = box2w(g - 4, 9, 2 * c), bx1 = box2w(g - 3, 7, 2 * c), bx2 = box2w(g - 4, 9, oh), bx3 = box2w(g - 3, 7, oh);
    uint32_t f7[9], f9a[9], f9b[9];
    const uint32_t fa = tb + T_7 + 4 * (8 + x);
#pragma unroll
    for (int m = 0; m < 9; m++) {
      f7[m] = lds32(fa + 32 * m);
      f9b[m] = lds32(fa + 320 + 32 * m);
      f9a[m] = lds32(fa + 316 + 32 * m);
    }
    mbar_wait(BAR(MB_EMPTY + 15));
    TS(36);
    uint32_t z09[8], z07[8], zm9[8], zm7[8];
#pragma unroll
    for (int i = 0; i < 8; i++) {
      uint32_t h[4];
      ldsm4(h, hb + 128 * i);
      float y0, y1, y2, y3, w0, w1, w2, w3;
      mma0(y0, y1, y2, y3, bx0, bx1, bx2, bx3, h[2], c < 2 ? h[3] : h[1]);
      mma0(w0, w1, w2, w3, bx0, bx1, bx2, bx3, h[1], c < 2 ? h[2] : h[0]);
      z09[i] = pack_bf(y0, y1); z07[i] = pack_bf(y2, y3);
      zm9[i] = pack_bf(w0, w1); zm7[i] = pack_bf(w2, w3);
    }
    float a[4][2][4];
#pragma unroll
    for (int kap = 0; kap < 4; kap++)
#pragma unroll
      for (int sg = 0; sg < 2; sg++)
#pragma unroll
        for (int bk = 3; bk >= kap; bk--) {
          const int m = 2 * (bk - kap) + 1;
          float(&a0)[4] = a[bk][0];
          float(&a1)[4] = a[bk][1];
          if (sg == 0 && kap == 0) {
            mma0(a0[0], a0[1], a0[2], a0[3], f9a[m], f9a[m + 1], f9a[m - 1], f9a[m], z09[0], z09[1]);
            mma0(a1[0], a1[1], a1[2], a1[3], f9b[m], f9b[m + 1], f9b[m - 1], f9b[m], zm9[0], zm9[1]);
          } else if (sg == 0) {
            mma(a0[0], a0[1], a0[2], a0[3], f9a[m], f9a[m + 1], f9a[m - 1], f9a[m], z09[2 * kap], z09[2 * kap + 1]);
            mma(a1[0], a1[1], a1[2], a1[3], f9b[m], f9b[m + 1], f9b[m - 1], f9b[m], zm9[2 * kap], zm9[2 * kap + 1]);
          } else {
            mma(a0[0], a0[1], a0[2], a0[3], f7[m], f7[m + 1], f7[m - 1], f7[m], zm7[2 * kap], zm7[2 * kap + 1]);
            mma(a1[0], a1[1], a1[2], a1[3], f7[m], f7[m + 1], f7[m - 1], f7[m], z07[2 * kap], z07[2 * kap + 1]);
          }
        }
#pragma unroll
    for (int bk = 0; bk < 4; bk++) {
      sts64(st + 256 * (8 + 2 * bk), pack_bf(a[bk][0][0], a[bk][0][1]), pack_bf(a[bk][1][0], a[bk][1][1]));
      sts64(st + 256 * (9 + 2 * bk), pack_bf(a[bk][0][2], a[bk][0][3]), pack_bf(a[bk][1][2], a[bk][1][3]));
    }
  }
  TS(44);
  {
    const int oh = c < 3 ? 2 * c : -10;
    const uint32_t bx0 = box2w(g - 10, 5, 2 * c - 8), bx1 = box2w(g - 5, 3, 2 * c - 8), bx2 = box2w(g - 10, 5, oh), bx3 = box2w(g - 5, 3, oh);
    const uint32_t lb0 = ((unsigned)(x + 5) < 2u ? kv : 0u) | ((unsigned)(x + 4) < 2u ? kv << 16 : 0u);
    const uint32_t lb1 = ((unsigned)(x - 3) < 2u ? kv : 0u) | ((unsigned)(x - 4) < 2u ? kv << 16 : 0u);
    const int q0 = g - 1, q1 = c < 3 ? g : g - 2;
    uint32_t y0a = ub + U_PAD + (q0 & 1) * U_ODD + 16 * (q0 >> 1) + 4 * c;
    uint32_t y1a = ub + U_PAD + (q1 & 1) * U_ODD + 16 * (q1 >> 1) + 4 * c;
    uint2 a5[10], a3[10];
    const uint32_t aa = tb + T_5 + 4 * (8 + 2 * g - 2 * c);
#pragma unroll
    for (int m = 0; m < 10; m++) { a5[m] = lds64(aa + 32 * m); a3[m] = lds64(aa + 384 + 32 * m); }
    float T[6][4];
#pragma unroll
    for (int i = 0; i < 6; i++) T[i][0] = T[i][1] = T[i][2] = T[i][3] = 0.f;
    uint32_t x5[2] = {0, 0}, x3[2] = {0, 0}, yb[4], lq[4];
    uint32_t lqa = qa, sta = st + 256 * 8;
    uint2 sv;
    auto fetch = [&]() {
      yb[0] = lds32(y0a); yb[1] = lds32(y1a); yb[2] = lds32(y0a + 64); yb[3] = lds32(y1a + 64);
      ldsm4(lq, lqa);
      sv = lds64(min(sta, st + 256 * 15));
      y0a += 128; y1a += 128; lqa += 128; sta += 256;
    };
    fetch();
#pragma unroll 2
    for (int kap = -1; kap < 13; kap++) {
      float yn[2][4];
      mma0(yn[0][0], yn[0][1], yn[0][2], yn[0][3], bx0, bx1, bx2, bx3, yb[0], yb[1]);
      mma0(yn[1][0], yn[1][1], yn[1][2], yn[1][3], bx0, bx1, bx2, bx3, yb[2], yb[3]);
      sts64_p(kap > 0, sta - 256 * 7, pack_bf(T[0][0], T[0][1]), pack_bf(T[0][2], T[0][3]));
#pragma unroll
      for (int i = 0; i < 5; i++)
        mmac_p((unsigned)kap < 12u - i, T[i], a5[2 * i + 1].x, a5[2 * i + 1].y, a5[2 * i].x, a5[2 * i].y, x5[0], x5[1], T[i + 1]);
      const float ci[4] = {bf_lo(sv.x), bf_hi(sv.x), bf_lo(sv.y), bf_hi(sv.y)};
      mmac_p(kap < 7, T[5], lq[0], lq[1], lq[2], lq[3], lb0, lb1, ci);
      fetch();
#pragma unroll
      for (int i = 0; i < 5; i++)
        mma_p((unsigned)kap < 12u - i, T[i], a3[2 * i + 1].x, a3[2 * i + 1].y, a3[2 * i].x, a3[2 * i].y, x3[0], x3[1]);
#pragma unroll
      for (int hh = 0; hh < 2; hh++) { x5[hh] = pack_bf(yn[hh][0], yn[hh][1]); x3[hh] = pack_bf(yn[hh][2], yn[hh][3]); }
    }
  }
  TS(45);
  {
    uint32_t F[66];
    const uint32_t fa = tb + T_D + 32 + 4 * x;
#pragma unroll
    for (int m = 0; m < 66; m++) F[m] = lds32(fa + 32 * m);
    float T[5][4];
#pragma unroll
    for (int i = 0; i < 5; i++) T[i][0] = T[i][1] = T[i][2] = T[i][3] = 0.f;
    uint32_t qd[8][4], held[2] = {0, 0};
    uint32_t qp = qa + 128 * 15, sta = st + 256 * 14;
    uint4* yd = ydst + 19 * 16;
#pragma unroll
    for (int i = 0; i < 6; i++) ldsm4(qd[i], qp - 16 * i);
    uint2 sv = lds64(sta + 256);
    float ci[4] = {bf_lo(sv.x), bf_hi(sv.x), bf_lo(sv.y), bf_hi(sv.y)};
    TS(46);
#pragma unroll 2
    for (int be = 15; be >= 0; be--) {
#pragma unroll
      for (int k = 4; k >= 1; k--)
        mmac_p(be <= 15 - k, T[k], qd[0][0], qd[0][1], qd[0][2], qd[0][3], F[16 * k + 1], F[16 * k], T[k - 1]);
      mmac(T[0], qd[0][0], qd[0][1], qd[0][2], qd[0][3], F[1], F[0], ci);
      ldsm4(qd[6], qp - 16 * 6);
      ldsm4(qd[7], qp - 16 * 7);
      sv = lds64(sta);
#pragma unroll
      for (int i = 1; i < 8; i++) {
#pragma unroll
        for (int k = 3; k >= 0; k--)
          mma_p(k == 0 || be <= 15 - k, T[k], qd[i][0], qd[i][1], qd[i][2], qd[i][3], F[16 * k + 2 * i + 1], F[16 * k + 2 * i]);
        if (i < 7) ldsm4(qd[i - 1], qp - 128 - 16 * (i - 1));
        if (i == 2) {
          const uint32_t w0 = pack_bf(T[4][0], T[4][1]), w1 = pack_bf(T[4][2], T[4][3]);
          st_x_p(be <= 10 && !(be & 1), yd, nz(w0), w1, held[0], held[1]);
          held[0] = w0; held[1] = w1;
        }
        if (i == 4) {
          if (be <= 4) sv = make_uint2(0, 0);
          ci[0] = bf_lo(sv.x); ci[1] = bf_hi(sv.x); ci[2] = bf_lo(sv.y); ci[3] = bf_hi(sv.y);
        }
      }
      qp -= 128; sta -= 256; yd -= 16;
    }
#pragma unroll
    for (int B = 1; B >= 0; B--)
      st_x(ydst + B * 32, nz(pack_bf(T[2 * B][0], T[2 * B][1])), pack_bf(T[2 * B][2], T[2 * B][3]),
           pack_bf(T[2 * B + 1][0], T[2 * B + 1][1]), pack_bf(T[2 * B + 1][2], T[2 * B + 1][3]));
  }
}

__device__ __forceinline__ void feat(const float (&acc)[48], int j0, const uint32_t (&wf)[4], uint32_t* w) {
  const uint32_t a0 = pack_bf(acc[4 * j0], acc[4 * j0 + 1]), a1 = pack_bf(acc[4 * j0 + 2], acc[4 * j0 + 3]);
  const uint32_t a2 = pack_bf(acc[4 * j0 + 4], acc[4 * j0 + 5]), a3 = pack_bf(acc[4 * j0 + 6], acc[4 * j0 + 7]);
  float p[8];
  mma0(p[0], p[1], p[2], p[3], a0, a1, a2, a3, wf[0], wf[1]);
  mma0(p[4], p[5], p[6], p[7], a0, a1, a2, a3, wf[2], wf[3]);
  w[0] = pack_bf(p[0], p[2]); w[1] = pack_bf(p[1], p[3]); w[2] = pack_bf(p[4], p[6]); w[3] = pack_bf(p[5], p[7]);
}
__device__ __forceinline__ void dual_softmax(const uint32_t* w, uint32_t* e) {
  const float L = 1.44268798828125f;
  uint32_t mx = bmax2(bmax2(w[0], w[1]), bmax2(w[2], w[3]));
  uint32_t mn = bmin2(bmin2(w[0], w[1]), bmin2(w[2], w[3]));
  mx = bmax2(mx, __shfl_xor_sync(0xffffffffu, mx, 1));
  mn = bmin2(mn, __shfl_xor_sync(0xffffffffu, mn, 1));
  mx = bmax2(mx, __shfl_xor_sync(0xffffffffu, mx, 2));
  mn = bmin2(mn, __shfl_xor_sync(0xffffffffu, mn, 2));
  const float mx0 = bf_lo(mx) * -L, mx1 = bf_hi(mx) * -L, mn0 = bf_lo(mn) * L, mn1 = bf_hi(mn) * L;
  float ep[2][4], em[2][4];
#pragma unroll
  for (int i = 0; i < 4; i++) {
    const float x0 = bf_lo(w[i]), x1 = bf_hi(w[i]);
    ep[0][i] = ex2(fmaf(x0, L, mx0)); em[0][i] = ex2(fmaf(x0, -L, mn0));
    ep[1][i] = ex2(fmaf(x1, L, mx1)); em[1][i] = ex2(fmaf(x1, -L, mn1));
  }
  __half2 sp = __floats2half2_rn((ep[0][0] + ep[0][1]) + (ep[0][2] + ep[0][3]), (ep[1][0] + ep[1][1]) + (ep[1][2] + ep[1][3]));
  __half2 sm = __floats2half2_rn((em[0][0] + em[0][1]) + (em[0][2] + em[0][3]), (em[1][0] + em[1][1]) + (em[1][2] + em[1][3]));
  sp = __hadd2(sp, __shfl_xor_sync(0xffffffffu, sp, 1));
  sm = __hadd2(sm, __shfl_xor_sync(0xffffffffu, sm, 1));
  sp = __hadd2(sp, __shfl_xor_sync(0xffffffffu, sp, 2));
  sm = __hadd2(sm, __shfl_xor_sync(0xffffffffu, sm, 2));
  const float rp[2] = {rcp(__low2float(sp)), rcp(__high2float(sp))}, rm[2] = {rcp(__low2float(sm)), rcp(__high2float(sm))};
#pragma unroll
  for (int i = 0; i < 4; i++) {
    const int r = i & 1, k = i & 2;
    e[i] = pack_bf(ep[r][k] * rp[r], ep[r][k + 1] * rp[r]);
    e[4 + i] = pack_bf(em[r][k] * rm[r], em[r][k + 1] * rm[r]);
  }
}

__global__ void __launch_bounds__(NTHREADS, 1)
fused_kernel(const Params P, const __grid_constant__ CUtensorMap mx, const __grid_constant__ CUtensorMap mw,
             const __grid_constant__ CUtensorMap mo, const __grid_constant__ CUtensorMap mu,
             const __grid_constant__ CUtensorMap mout) {
  constexpr uint32_t sb = SB;
  const int tid = threadIdx.x, lane = tid & 31;
  const int warp = __shfl_sync(0xffffffffu, tid >> 5, 0);
  const int b = blockIdx.x, oct = b >> 3, i8 = b & 7;
  const int rt = oct < 8 ? oct : 15 - oct;
  const int hp = (oct >> 3) * 8 + i8;

  const int d = b * 4 + ((tid >> 5) & 3);
  KgenRaw raw = {}, raw3 = {};
  unsigned short dsk = 0;
  if (tid < 384) {
    asm volatile("prefetch.tensormap [%0];" ::"l"(&mu) : "memory");
    asm volatile("prefetch.tensormap [%0];" ::"l"(&mw) : "memory");
    asm volatile("prefetch.tensormap [%0];" ::"l"(&mx) : "memory");
    raw = kgen_load(P, d, tid >> 7, lane);
    raw3 = kgen_load(P, d, 3, lane);
    dsk = __ldg((const unsigned short*)P.Dskip + d);
  }
  if (warp >= 12) asm volatile("setmaxnreg.dec.sync.aligned.u32 32;");
  if (warp == 12) {
    if (lane == 0) {
#pragma unroll
      for (int i = 0; i < 9; i++) mbar_init(BAR(i), 1);
      asm volatile("fence.mbarrier_init.release.cluster;" ::: "memory");
    }
    __syncwarp();
    if (lane < 9) mbar_expect(BAR(0) + 8 * lane, lane == 0 ? 16384 : (lane < 8 ? 28672 : 29696));
    __syncwarp();
    nb_arrive(NB_PREP, 448);
#pragma unroll 1
    for (int kb = 0; kb < 8; kb++) {
      if (kb == STEP_U) e_tma5d(sb + OFF_STG0, &mu, BAR(MB_URAW), i8 * 64, oct * 4);
      e_tma3d(sb + OFF_W + kb * 12288, &mw, BAR(MB_FULL) + 8 * kb, hp * 32, kb * 64, 0);
      if (kb < 5) e_tma2d(sb + OFF_X + (kb < 2 ? kb + 3 : kb - 2) * 16384, &mx, BAR(MB_FULL) + 8 * kb, kb * 64, rt * 256);
    }
    if (smem_u32(smem_raw) != SB) __trap();
  }
  if (warp >= 12) {
    if (warp == 12) {
      nb_sync(NB_PROD, 64);
      e_prefetch(P.x + (size_t)(rt * 256 + hp * 16) * 512, 16384);
      e_bulk(sb + OFF_PHI, P.wphi + hp * 512, 1024, BAR(MB_FULL + 7));
      uint32_t slot = sb + OFF_X + 3 * 16384;
#pragma unroll 1
      for (int n = 0; n < 11; n++) {
        mbar_wait(BAR(MB_EMPTY) + 8 * n);
        const int m = n + 5;
        e_tma2d(slot, &mx, BAR(MB_FULL) + 8 * m, (m & 7) * 64, rt * 256 + (m >> 3) * 128);
        slot = slot == sb + OFF_X + 4 * 16384 ? sb + OFF_X : slot + 16384;
        if (n == 7) e_prefetch(P.wo + (size_t)b * 2048, 4096);
      }
#pragma unroll 1
      for (int i = 0; i < 8; i++) {
        mbar_wait(BAR(MB_EMPTY + 10) + 8 * ((0x54332100u >> (4 * i)) & 7));
        const int w0 = (0x54736210u >> (4 * i)) & 7;
        const int col = (hp & 3) * 128 + (w0 >> 2) * 64;
        e_tma2d(sb + OFF_W + w0 * 16384, &mo, BAR(MB_WO) + 8 * (w0 >> 2), col, w0 * 64);
        e_tma2d(sb + OFF_W + w0 * 16384 + 8192, &mo, BAR(MB_WO) + 8 * (w0 >> 2), col ^ 64, w0 * 64);
      }
    } else {
      if (warp == 13) {
        if (lane == 0) {
#pragma unroll
          for (int i = 9; i < 38; i++) mbar_init(BAR(i), i < MB_EMPTY ? 1 : (i < MB_CLOSE ? 4 : 12));
          asm volatile("fence.mbarrier_init.release.cluster;" ::: "memory");
        }
        __syncwarp();
        if (lane < 10) mbar_expect(BAR(MB_FULL + 8) + 8 * lane, lane < 8 ? 16384 : 65536);
        __syncwarp();
        nb_arrive(NB_PROD, 64);
        nb_arrive(NB_PREP, 448);
        nb_arrive(NB_ZERO, 96);
        const unsigned cnt0 = ld_x32((const uint32_t*)P.xs);
        nb_sync(NB_INIT, 224);
        if (lane == 0) TS1(49);
        if (lane == 0) asm volatile("red.release.gpu.global.add.u32 [%0], 1;" ::"l"(P.xs) : "memory");
        if (lane == 0) TS1(50);
#pragma unroll 1
        for (int i = 0; i < SPIN_MAX; i++) {
          unsigned v;
          asm volatile("ld.acquire.gpu.global.u32 %0, [%1];" : "=r"(v) : "l"(P.xs) : "memory");
          if ((int)(v - ((cnt0 & ~(unsigned)(NCTA - 1)) + NCTA)) >= 0) break;
          __nanosleep(200);
        }
        if (lane == 0) TS1(51);
        asm volatile("fence.proxy.async.global;" ::: "memory");
        mbar_wait(BAR(MB_EMPTY + 11));
        sts128(sb + OFF_U + (lane >> 4) * U_CH + ((lane >> 3) & 1) * U_ODD + (lane & 7) * 16, 0, 0, 0, 0);
        sts128(sb + OFF_U + (2 + (lane >> 4)) * U_CH + ((lane >> 3) & 1) * U_ODD + (lane & 7) * 16, 0, 0, 0, 0);
        __syncwarp();
        e_expect(BAR(MB_UFULL), 16384);
#pragma unroll 1
        for (int i = 0; i < 8; i++)
          e_bulk(sb + OFF_U + (i >> 1) * U_CH + (i & 1) * U_ODD + U_PAD, P.xs + X_UT + (b * 8 + i) * 128, 2048, BAR(MB_UFULL));
      } else {
        if (ZERO_STEP) { nb_sync(NB_ZERO, 96); mbar_wait(BAR(MB_EMPTY + ZERO_STEP - 1)); } else { nb_arrive(NB_ZERO, 96); }
        uint4* po = P.xs + X_O + (rt * 4 * 32 + hp * 2) * 128;
        uint4* py = P.xs + X_Y + b * 1024;
        uint4* pp = P.xs + X_PART + (hp * 8 + rt) * 144;
#pragma unroll 1
        for (int i = tid - 448; i < 1024; i += 64) {
          st_x(po + (i >> 8) * 4096 + (i & 255), 0, 0, 0, 0);
          st_x(py + i, 0, 0, 0, 0);
          if (i < 144) st_x(pp + i, 0, 0, 0, 0);
        }
        nb_arrive(NB_INIT, 224);
        if (tid == 448) TS1(55);
      }
    }
    return;
  }

  asm volatile("setmaxnreg.inc.sync.aligned.u32 160;");
  const int wg = warp >> 2, w = warp & 3, t = tid & 127;
  const int g = lane >> 2, c = lane & 3;
  const uint32_t tb = sb + OFF_T + w * T_CH;
  {
    float k[5][4], k2048 = 0.f, dt;
#pragma unroll
    for (int j = 0; j < 5; j++) k[j][0] = k[j][1] = k[j][2] = k[j][3] = 0.f;
    const uint32_t kp = tb + (wg & 1) * 2608;
#pragma unroll 1
    for (int r = 0; r <= (wg >> 1); r++) {
      kgen_unit(raw, lane, wg == 2 ? sb + OFF_STG0 + 16384 + w * 2048 : (kp + 127) & ~127u, r ? BAR(MB_EMPTY + 7) : 0u, dt, k, k2048);
      raw = raw3;
      TS(40 + wg + r);
      if (r == 0) {
        if (wg != 2) {
#pragma unroll
          for (int j = 0; j < 5; j++) sts128(kp + j * 512 + lane * 16, fu(k[j][0]), fu(k[j][1]), fu(k[j][2]), fu(k[j][3]));
          k2048 += __shfl_xor_sync(0xffffffffu, k2048, 16);
          k2048 += __shfl_xor_sync(0xffffffffu, k2048, 8);
          if (lane < 8) sts32(kp + 2560 + lane * 4, fu(k2048));
        } else if ((fu(k[0][0]) & fu(k[1][0]) & fu(k[2][0]) & fu(k[3][0]) & fu(k[4][0])) == 0xffffffffu) {
          sts32(kp, 0);
        }
        nb_sync(NB_PREP, 448);
        if (wg == 2) {
#pragma unroll 1
          for (int q = 0; q < 2; q++) {
            const uint32_t src = tb + q * 2608;
#pragma unroll
            for (int j = 0; j < 5; j++) {
              const uint4 v = lds128(src + j * 512 + lane * 16);
              k[j][0] += uf(v.x); k[j][1] += uf(v.y); k[j][2] += uf(v.z); k[j][3] += uf(v.w);
            }
            if (lane < 8) k2048 += uf(lds32(src + 2560 + lane * 4));
          }
        }
      }
    }
    if (wg == 2) {
      if (lane == 0 && (fu(k[0][0]) & fu(k[1][0]) & fu(k[2][0]) & fu(k[3][0]) & fu(k[4][0])) != 0xffffffffu)
        mbar_arrive(BAR(MB_CLOSE));
      TS(34);
#pragma unroll
      for (int o2 = 16; o2; o2 >>= 1) k2048 += __shfl_xor_sync(0xffffffffu, k2048, o2);
      const float sc = 2.f * dt;
#pragma unroll
      for (int j = 0; j < 5; j++) { k[j][0] *= sc; k[j][1] *= sc; k[j][2] *= sc; k[j][3] *= sc; }
      k2048 *= sc;
      if (lane == 0) k[0][0] += bf_lo(dsk);
      build_tables(tb, lane, k, k2048);
      TS(35);
      mbar_wait(BAR(MB_UFULL));
      uint4* const g_y = P.xs + X_Y;
      conv_channel(sb + OFF_U + w * U_CH, tb, lane, g_y + (size_t)d * 256 + lane);
      nb_arrive(NB_BDONE, 384);
      TS(37);
      const int lam = w * 8 + g;
      const uint4* src = g_y + (size_t)(oct * 32 + c * 8) * 256 + i8 * 32 + lam;
      uint4 v[8];
#pragma unroll 1
      for (int it = 0; it < SPIN_MAX; it++) {
        uint32_t m = 0xffffffffu;
#pragma unroll
        for (int i = 0; i < 8; i++) v[i] = ld_x(src + i * 256);
#pragma unroll
        for (int i = 0; i < 8; i++) m = min(m, v[i].x);
        if (__all_sync(0xffffffffu, m != 0)) break;
      }
      __nv_bfloat16* dst = P.out + (size_t)(i8 * 256 + (lam >> 2) * 16 + (lam & 3) * 2) * 1024 + 512 + oct * 32 + c * 8;
#pragma unroll
      for (int i = 0; i < 8; i++) *(uint4*)(dst + (size_t)((i >> 2) * 128 + ((i >> 1) & 1) * 8 + (i & 1)) * 1024) = tr_row(v, i);
      TS(38);
      GT(63);
      return;
    }
    if (wg == 1) {
      mbar_wait(BAR(MB_URAW));
      TS(48);
      uint4* dst = P.xs + X_UT + (i8 * 64 + g) * 256 + (c & 1) * 128 + oct * 8 + w * 2 + (c >> 1);
      uint32_t r[8][4];
#pragma unroll
      for (int i = 0; i < 8; i++) ldsm4t(r[i], sb + OFF_STG0 + w * 4096 + lane * 128 + (((i ^ lane) & 7) << 4));
#pragma unroll
      for (int i = 0; i < 8; i++) dst[i * 2048] = make_uint4(r[i][0], r[i][1], r[i][2], r[i][3]);
      nb_arrive(NB_INIT, 224);
      if (lane == 0) mbar_arrive(BAR(MB_CLOSE));
      mbar_wait(BAR(MB_CLOSE));
    }
    TS(wg * 16 + 1);
  }

  float acc[2][48];
  {
    uint32_t fb = BAR(MB_FULL) + 64 * wg;
    uint32_t da = (uint32_t)mkdesc(sb + OFF_X, 16, 0, 0) + (wg ? 1024 : 3072), db = (uint32_t)mkdesc(sb + OFF_W, 4096, 0, 0);
    constexpr uint64_t ha = mkdesc(0, 0, 1024, 1), hb = mkdesc(0, 0, 512, 2);
#pragma unroll 1
    for (int kb = 0; kb < 8; kb++) {
      mbar_wait(fb);
      if (kb == 0) TS(wg * 16 + 2);
      WG_FENCE();
#pragma unroll
      for (int k = 0; k < 4; k++) {
        wgmma_ss_n96(acc[0], ha | (da + 2 * k), hb | (db + 64 * k), k ? 1 : kb);
        wgmma_ss_n96(acc[1], ha | (da + 2 * k + 512), hb | (db + 64 * k), k ? 1 : kb);
      }
      WG_COMMIT();
      WG_WAIT(1);
      if (kb > 0 && lane == 0) mbar_arrive(fb + 8 * (MB_EMPTY - MB_FULL - 1));
      fb += 8; db += 768;
      da = da == (uint32_t)mkdesc(sb + OFF_X + 65536, 16, 0, 0) ? da - 4096 : da + 1024;
    }
    WG_WAIT(0);
    if (lane == 0) mbar_arrive(fb + 8 * (MB_EMPTY - MB_FULL - 1));
    mbar_wait(fb + 8 * (MB_EMPTY - MB_FULL - 1));
  }
  uint32_t wf[2][4];
  ldsm4t(wf[0], sb + OFF_PHI + (lane & 15) * 32 + (lane >> 4) * 16);
  ldsm4t(wf[1], sb + OFF_PHI + 512 + (lane & 15) * 32 + (lane >> 4) * 16);
  TS(wg * 16 + 3);

  uint32_t pw[32], eq[32];
#pragma unroll
  for (int u = 0; u < 4; u++)
#pragma unroll
    for (int h = 0; h < 2; h++) feat(acc[u & 1], (u < 2 ? 4 : 0) + 2 * h, wf[h], pw + 8 * u + 4 * h);
  {
    uint32_t all = 0xffffffffu;
#pragma unroll
    for (int i = 0; i < 16; i++) all &= pw[2 * i];
    if (wg == 0 && lane == 0 && all != 0xffffffffu) mbar_arrive(BAR(MB_CLOSE));
  }
  mbar_wait(BAR(MB_CLOSE));
  const uint32_t stg0 = sb + OFF_STG0, stg1 = sb + OFF_X + 32768;
  uint32_t sl = (wg ? stg1 : stg0) + w * 3072 + lane * 16;
#pragma unroll
  for (int mt = 0; mt < 2; mt++)
#pragma unroll
    for (int h = 0; h < 2; h++) {
      const float* a = acc[mt] + 32 + 8 * h;
      stsm4(sl + mt * 12288 + 2048 + h * 512, pack_bf(a[0], a[1]), pack_bf(a[2], a[3]), pack_bf(a[4], a[5]), pack_bf(a[6], a[7]));
    }
#pragma unroll 1
  for (int u = 0; u < 4; u++) {
#pragma unroll
    for (int i = 0; i < 16; i++) eq[i] = eq[16 + i];
    dual_softmax(pw, eq + 16);
    dual_softmax(pw + 4, eq + 24);
    if (u < 2) {
#pragma unroll
      for (int i = 0; i < 4; i++) stsm4(sl + i * 512, eq[16 + 4 * i], eq[17 + 4 * i], eq[18 + 4 * i], eq[19 + 4 * i]);
      if (wg) nb_arrive(NB_ST0 + u, 256);
      sl += 12288;
    }
#pragma unroll
    for (int i = 0; i < 24; i++) pw[i] = pw[i + 8];
  }
  TS(wg * 16 + 4);
  uint4* const g_part = P.xs + X_PART;
  uint4* const g_o = P.xs + X_O;
  const uint32_t kvs = stg0;
  if (wg == 0) {
    nb_sync(NB_WG0, 128);
    mbar_wait(BAR(MB_UFULL));
    mbar_wait(BAR(MB_EMPTY + 15));
    float kv[12];
#pragma unroll
    for (int i = 0; i < 12; i++) kv[i] = 0.f;
    const int mi = lane >> 3;
    const uint32_t ao = w * 512 + (lane & 7) * 16 + ((mi & 1) * 2 + (mi >> 1)) * 128, bo = 2048 + (w >> 1) * 512 + lane * 16;
#pragma unroll 1
    for (int j = 0; j < 4; j++) {
      if (j >= 2) nb_sync(NB_ST0 + j - 2, 256);
      const uint32_t sg = (j >= 2 ? stg1 : stg0) + (j & 1) * 12288;
      uint32_t a[4][4], bb[4][4];
#pragma unroll
      for (int s = 0; s < 4; s++) { ldsm4t(a[s], sg + s * 3072 + ao); ldsm4t(bb[s], sg + s * 3072 + bo); }
#pragma unroll
      for (int s = 0; s < 4; s++) {
        mma(kv[0], kv[1], kv[2], kv[3], a[s][0], a[s][1], a[s][2], a[s][3], bb[s][0], bb[s][1]);
        mma(kv[4], kv[5], kv[6], kv[7], a[s][0], a[s][1], a[s][2], a[s][3], bb[s][2], bb[s][3]);
        mma(kv[8], kv[9], kv[10], kv[11], a[s][0], a[s][1], a[s][2], a[s][3], 0x3F803F80u, 0x3F803F80u);
      }
    }
    uint4* pp = g_part + (size_t)(hp * 8 + rt) * 144;
    st_x(pp + t, nz(pack_bf(kv[0], kv[1])), pack_bf(kv[2], kv[3]), pack_bf(kv[4], kv[5]), pack_bf(kv[6], kv[7]));
    if (c < 2) st_x32((uint32_t*)(pp + 128) + w * 16 + c * 8 + g, nz(fu(c ? kv[10] : kv[8])));
    TS(5);
    const uint4* ps = g_part + (size_t)hp * 8 * 144 + t;
    const uint32_t* zs = (const uint32_t*)(g_part + (size_t)(hp * 8 + (lane >> 4) * 4) * 144 + 128) + w * 16 + (lane & 15);
    uint4 v[8];
    uint32_t zv[4];
#pragma unroll 1
    for (int it = 0; it < SPIN_MAX; it++) {
#pragma unroll
      for (int i = 0; i < 8; i++) v[i] = ld_x(ps + i * 144);
#pragma unroll
      for (int i = 0; i < 4; i++) zv[i] = ld_x32(zs + i * 576);
      uint32_t m = min(min(zv[0], zv[1]), min(zv[2], zv[3]));
#pragma unroll
      for (int i = 0; i < 8; i++) m = min(m, v[i].x);
      if (__all_sync(0xffffffffu, m != 0)) break;
    }
    float s4[4][4];
#pragma unroll
    for (int i = 0; i < 4; i++) s4[i][0] = s4[i][1] = s4[i][2] = s4[i][3] = 0.f;
    const uint32_t eye = (g >> 1) == c ? ((g & 1) ? 0x3F800000u : 0x3F80u) : 0u;
#pragma unroll
    for (int r = 0; r < 8; r++) {
      mma_k8(s4[(r & 1) * 2], v[r].x, v[r].y, eye);
      mma_k8(s4[(r & 1) * 2 + 1], v[r].z, v[r].w, eye);
    }
    float s[8];
#pragma unroll
    for (int i = 0; i < 8; i++) s[i] = s4[i >> 2][i & 3] + s4[2 + (i >> 2)][i & 3];
    float zsum = (uf(zv[0]) + uf(zv[1])) + (uf(zv[2]) + uf(zv[3]));
    zsum += __shfl_xor_sync(0xffffffffu, zsum, 16);
    stsm4(kvs + w * 512 + lane * 16, pack_bf(s[0], s[1]), pack_bf(s[2], s[3]), pack_bf(s[4], s[5]), pack_bf(s[6], s[7]));
    if (lane < 16) sts16(kvs + 2048 + (w * 16 + lane) * 2, pack_bf(zsum, 0.f));
    TS(6);
  }
  nb_sync(NB_KV, 256);
  {
    uint32_t kb_[4][4], zb[8];
#pragma unroll
    for (int i = 0; i < 4; i++) ldsm4t(kb_[i], kvs + i * 512 + lane * 16);
#pragma unroll
    for (int i = 0; i < 8; i++) zb[i] = lds32(kvs + 2048 + i * 16 + c * 4);
    uint4* od = g_o + (size_t)((rt * 4 + wg * 2) * 32 + hp * 2) * 128 + t;
#pragma unroll 1
    for (int mt = 0; mt < 2; mt++) {
#pragma unroll
      for (int h = 0; h < 2; h++) {
        const uint32_t* e = eq + 8 * h;
        float n[8], dn[4];
        mma0(dn[0], dn[1], dn[2], dn[3], e[0], e[1], e[2], e[3], zb[4 * h], zb[4 * h + 1]);
        mma0(n[0], n[1], n[2], n[3], e[0], e[1], e[2], e[3], kb_[2 * h][0], kb_[2 * h][1]);
        mma0(n[4], n[5], n[6], n[7], e[0], e[1], e[2], e[3], kb_[2 * h][2], kb_[2 * h][3]);
        mma(dn[0], dn[1], dn[2], dn[3], e[4], e[5], e[6], e[7], zb[4 * h + 2], zb[4 * h + 3]);
        mma(n[0], n[1], n[2], n[3], e[4], e[5], e[6], e[7], kb_[2 * h + 1][0], kb_[2 * h + 1][1]);
        mma(n[4], n[5], n[6], n[7], e[4], e[5], e[6], e[7], kb_[2 * h + 1][2], kb_[2 * h + 1][3]);
        const float r0 = rcp(dn[0] + 1e-6f), r1 = rcp(dn[2] + 1e-6f);
        st_x(od + h * 128, nz(pack_bf(n[0] * r0, n[1] * r0)), pack_bf(n[2] * r1, n[3] * r1), pack_bf(n[4] * r0, n[5] * r0),
             pack_bf(n[6] * r1, n[7] * r1));
      }
#pragma unroll
      for (int i = 0; i < 16; i++) eq[i] = eq[16 + i];
      od += 4096;
    }
  }
  TS(wg * 16 + 7);
  const int rb = rt * 4 + (hp >> 2);
  const uint4* osrc = g_o + (size_t)(rb * 32 + wg * 16) * 128 + t;
  uint4 af[16];
  {
    const uint32_t* probe = (const uint32_t*)(osrc - lane + (lane & 15) * 128 + (lane >> 4) * 31);
#pragma unroll 1
    for (int it = 0; it < SPIN_MAX; it++) {
      uint32_t m = ld_x32(probe);
#pragma unroll
      for (int i = 0; i < 4; i++) af[i] = ld_x(osrc + i * 128);
#pragma unroll
      for (int i = 0; i < 4; i++) m = min(m, af[i].x);
      if (__all_sync(0xffffffffu, m != 0)) break;
    }
  }
#pragma unroll
  for (int i = 4; i < 16; i++) af[i] = ld_x(osrc + i * 128);
  TS(wg * 16 + 8);
  mbar_wait(BAR(MB_WO) + 8 * wg);
  nb_sync(NB_BDONE, 384);
  TS(wg * 16 + 9);
  float oc[64];
  {
    const uint64_t db = mkdesc(sb + OFF_W, 8192, 1024, 1) + wg * 4096;
#pragma unroll
    for (int j = 0; j < 4; j++) {
      if (j) {
#pragma unroll 1
        for (int it = 0; it < SPIN_MAX; it++) {
          const uint32_t m = min(min(af[4 * j].x, af[4 * j + 1].x), min(af[4 * j + 2].x, af[4 * j + 3].x));
          if (__all_sync(0xffffffffu, m != 0)) break;
#pragma unroll
          for (int i = 0; i < 4; i++) af[4 * j + i] = ld_x(osrc + (4 * j + i) * 128);
        }
      }
      WG_FENCE();
#pragma unroll
      for (int k = 0; k < 4; k++) wgmma_rs_n128(oc, af[4 * j + k], db + 128 * k + 1024 * j, j | k);
    }
    WG_COMMIT();
    WG_WAIT(0);
  }
  TS(wg * 16 + 10);
  const uint32_t xo = stg1 + wg * 16384 + t * 16, xi = stg1 + (wg ^ 1) * 16384 + t * 16;
#pragma unroll
  for (int i = 0; i < 8; i++) sts128(xo + i * 2048, fu(oc[32 + 4 * i]), fu(oc[33 + 4 * i]), fu(oc[34 + 4 * i]), fu(oc[35 + 4 * i]));
  nb_sync(NB_RED, 256);
  const uint32_t ot = stg0 + warp * 2048;
#pragma unroll
  for (int i = 0; i < 8; i += 2) {
    const uint4 v0 = lds128(xi + i * 2048), v1 = lds128(xi + i * 2048 + 2048);
    stsm4(ot + (lane & 15) * 128 + (((i + (lane >> 4)) ^ (lane & 7)) << 4),
          pack_bf(oc[4 * i] + uf(v0.x), oc[4 * i + 1] + uf(v0.y)), pack_bf(oc[4 * i + 2] + uf(v0.z), oc[4 * i + 3] + uf(v0.w)),
          pack_bf(oc[4 * i + 4] + uf(v1.x), oc[4 * i + 5] + uf(v1.y)), pack_bf(oc[4 * i + 6] + uf(v1.z), oc[4 * i + 7] + uf(v1.w)));
  }
  asm volatile("fence.proxy.async.shared::cta;" ::: "memory");
  __syncwarp();
  e_store2d(&mout, ot, (hp & 3) * 128 + wg * 64, rb * 64 + w * 16);
  TS(wg * 16 + 11);
  GT(61 + wg);
}

typedef CUresult (*EncodeFn)(CUtensorMap*, CUtensorMapDataType, cuuint32_t, void*, const cuuint64_t*, const cuuint64_t*,
                             const cuuint32_t*, const cuuint32_t*, CUtensorMapInterleave, CUtensorMapSwizzle,
                             CUtensorMapL2promotion, CUtensorMapFloatOOBfill);

}

extern "C" void kernel_launch(void* const* d_in, const int* in_sizes, int n_in, void* d_out, int out_size) {
  (void)in_sizes; (void)n_in; (void)out_size;
  void* fn = nullptr;
  cudaDriverEntryPointQueryResult qr;
  cudaGetDriverEntryPoint("cuTensorMapEncodeTiled", &fn, cudaEnableDefault, &qr);
  EncodeFn enc = (EncodeFn)fn;
  CUtensorMap mx, mw, mo, mu, mout;
  const cuuint32_t es[5] = {1, 1, 1, 1, 1};
  {
    cuuint64_t dims[2] = {512, 2048}, st[1] = {1024};
    cuuint32_t box[2] = {64, 128};
    enc(&mx, CU_TENSOR_MAP_DATA_TYPE_BFLOAT16, 2, d_in[0], dims, st, box, es, CU_TENSOR_MAP_INTERLEAVE_NONE,
        CU_TENSOR_MAP_SWIZZLE_128B, CU_TENSOR_MAP_L2_PROMOTION_L2_128B, CU_TENSOR_MAP_FLOAT_OOB_FILL_NONE);
  }
  {
    cuuint64_t dims[3] = {512, 512, 3}, st[2] = {3072, 1024};
    cuuint32_t box[3] = {32, 64, 3};
    enc(&mw, CU_TENSOR_MAP_DATA_TYPE_BFLOAT16, 3, d_in[1], dims, st, box, es, CU_TENSOR_MAP_INTERLEAVE_NONE,
        CU_TENSOR_MAP_SWIZZLE_64B, CU_TENSOR_MAP_L2_PROMOTION_L2_128B, CU_TENSOR_MAP_FLOAT_OOB_FILL_NONE);
  }
  {
    cuuint64_t dims[2] = {512, 512}, st[1] = {1024};
    cuuint32_t box[2] = {64, 64};
    enc(&mo, CU_TENSOR_MAP_DATA_TYPE_BFLOAT16, 2, d_in[3], dims, st, box, es, CU_TENSOR_MAP_INTERLEAVE_NONE,
        CU_TENSOR_MAP_SWIZZLE_128B, CU_TENSOR_MAP_L2_PROMOTION_L2_128B, CU_TENSOR_MAP_FLOAT_OOB_FILL_NONE);
  }
  {
    cuuint64_t dims[5] = {512, 2, 4, 4, 64}, st[4] = {1024, 8192, 2048, 32768};
    cuuint32_t box[5] = {64, 2, 4, 4, 4};
    enc(&mu, CU_TENSOR_MAP_DATA_TYPE_BFLOAT16, 5, d_in[4], dims, st, box, es, CU_TENSOR_MAP_INTERLEAVE_NONE,
        CU_TENSOR_MAP_SWIZZLE_128B, CU_TENSOR_MAP_L2_PROMOTION_L2_128B, CU_TENSOR_MAP_FLOAT_OOB_FILL_NONE);
  }
  {
    cuuint64_t dims[2] = {1024, 2048}, st[1] = {2048};
    cuuint32_t box[2] = {64, 16};
    enc(&mout, CU_TENSOR_MAP_DATA_TYPE_BFLOAT16, 2, d_out, dims, st, box, es, CU_TENSOR_MAP_INTERLEAVE_NONE,
        CU_TENSOR_MAP_SWIZZLE_128B, CU_TENSOR_MAP_L2_PROMOTION_NONE, CU_TENSOR_MAP_FLOAT_OOB_FILL_NONE);
  }
  Params P;
  P.x = (const __nv_bfloat16*)d_in[0];
  P.wphi = (const __nv_bfloat16*)d_in[2];
  P.wo = (const __nv_bfloat16*)d_in[3];
  P.logA = (const __nv_bfloat16*)d_in[5];
  P.Aim = (const __nv_bfloat16*)d_in[6];
  P.Cre = (const __nv_bfloat16*)d_in[7];
  P.Cim = (const __nv_bfloat16*)d_in[8];
  P.logdt = (const __nv_bfloat16*)d_in[9];
  P.Dskip = (const __nv_bfloat16*)d_in[10];
  P.out = (__nv_bfloat16*)d_out;
  cudaGetSymbolAddress((void**)&P.xs, g_x);
  P.ts = nullptr;
  cudaFuncSetAttribute(fused_kernel, cudaFuncAttributeMaxDynamicSharedMemorySize, SMEM_BYTES);
  fused_kernel<<<NCTA, NTHREADS, SMEM_BYTES>>>(P, mx, mw, mo, mu, mout);
}
```

```cpp
#include <cuda_runtime.h>
#include <cuda_bf16.h>
#include <cuda_fp16.h>
#include <cuda.h>
#include <stdint.h>

#define DBG_TS 0

namespace {

constexpr int NTHREADS = 512;
constexpr int NCTA = 128;
constexpr int OFF_W = 0;
constexpr int OFF_X = 98304;
constexpr int OFF_U = OFF_X + 65536;
constexpr int U_CH = 4416, U_ODD = 2240, U_PAD = 128;
constexpr int OFF_STG0 = OFF_U + 18432;
constexpr int OFF_T = OFF_STG0 + 24576;
constexpr int T_CH = 5216;
constexpr int T_D = 0;
constexpr int T_5 = 2144;
constexpr int T_3 = T_5 + 384;
constexpr int T_7 = T_5 + 1024;
constexpr int T_9 = T_7 + 320;
constexpr int T_KC = T_9 + 320;
constexpr int T_ST = T_5 - 1024;
constexpr int OFF_PHI = OFF_T + 4 * T_CH;
constexpr int OFF_BAR = OFF_PHI + 1024;
constexpr int SMEM_BYTES = OFF_BAR + 512;
constexpr uint32_t SB = 1024;
static_assert(T_KC + 2 * 656 <= T_CH, "table size");
static_assert(SMEM_BYTES <= 232448, "smem");
constexpr int MB_URAW = 0, MB_FULL = 1  , MB_WO = 17, MB_UFULL = 18, MB_OA = 19, MB_OB = 20,
              MB_EMPTY = 21  , MB_CLOSE = 37;
__host__ __device__ constexpr uint32_t BAR(int i) { return SB + OFF_BAR + 8 * i; }
constexpr int NB_WG0 = 1, NB_ODONE = 2, NB_ST0 = 3  , NB_KV = 5, NB_YZ = 6, NB_INIT = 7, NB_PREP = 8, NB_PROD = 9, NB_RDY = 10, NB_BDONE = 11, NB_ZERO = 12;
#define ZERO_N 1024
#define ZERO_STEP 7
#define STEPU 0
#define STEPPF 0
constexpr int STEP_PF = STEPPF, STEP_U = STEPU;
constexpr int SPIN_MAX = 1 << 16;

constexpr int X_CNT = 0;
constexpr int X_PART = 128;
constexpr int X_O = X_PART + 16 * 8 * 144;
constexpr int X_Y = X_O + 32 * 32 * 128;
constexpr int X_UT = X_Y + 512 * 8 * 32;
constexpr int X_SIZE = X_UT + 512 * (U_CH / 16);
__device__ __align__(128) uint4 g_x[X_SIZE];
extern __shared__ uint8_t smem_raw[];
#define TS(i) do {} while (0)
#define TS1(i) do {} while (0)
#define GT(i) do {} while (0)

__device__ __forceinline__ uint32_t smem_u32(const void* p) { return (uint32_t)__cvta_generic_to_shared(p); }
__device__ __forceinline__ void mbar_arrive(uint32_t b) {
  asm volatile("mbarrier.arrive.shared::cta.b64 _, [%0];" ::"r"(b) : "memory");
}
__device__ __forceinline__ void mbar_wait(uint32_t b) {
  uint32_t done = 0;
#pragma unroll 1
  for (int i = 0; i < SPIN_MAX && !done; i++) {
    asm volatile("{\n.reg .pred p;\nmbarrier.try_wait.parity.shared::cta.b64 p, [%1], 0, 4000;\nselp.u32 %0, 1, 0, p;\n}\n"
                 : "=r"(done) : "r"(b) : "memory");
  }
}
__device__ __forceinline__ void mbar_init(uint32_t b, int n) {
  asm volatile("mbarrier.init.shared::cta.b64 [%0], %1;" ::"r"(b), "r"(n) : "memory");
}
__device__ __forceinline__ void mbar_expect(uint32_t b, int bytes) {
  asm volatile("mbarrier.arrive.expect_tx.shared::cta.b64 _, [%0], %1;" ::"r"(b), "r"(bytes) : "memory");
}
__device__ __forceinline__ void nb_sync(int id, int n) { asm volatile("bar.sync %0, %1;" ::"r"(id), "r"(n) : "memory"); }
__device__ __forceinline__ void nb_arrive(int id, int n) { asm volatile("bar.arrive %0, %1;" ::"r"(id), "r"(n) : "memory"); }
#define ELECT "{\n.reg .pred p;\nelect.sync _|p, 0xffffffff;\n@p "
__device__ __forceinline__ void e_expect(uint32_t b, int bytes) {
  asm volatile(ELECT "mbarrier.arrive.expect_tx.shared::cta.b64 _, [%0], %1;\n}\n" ::"r"(b), "r"(bytes) : "memory");
}
__device__ __forceinline__ void e_tma2d(uint32_t dst, const CUtensorMap* m, uint32_t bar, int c0, int c1) {
  asm volatile(ELECT "cp.async.bulk.tensor.2d.shared::cluster.global.mbarrier::complete_tx::bytes [%0], [%1, {%3,%4}], [%2];\n}\n"
               ::"r"(dst), "l"(m), "r"(bar), "r"(c0), "r"(c1) : "memory");
}
__device__ __forceinline__ void e_tma3d(uint32_t dst, const CUtensorMap* m, uint32_t bar, int c0, int c1, int c2) {
  asm volatile(ELECT "cp.async.bulk.tensor.3d.shared::cluster.global.mbarrier::complete_tx::bytes [%0], [%1, {%3,%4,%5}], [%2];\n}\n"
               ::"r"(dst), "l"(m), "r"(bar), "r"(c0), "r"(c1), "r"(c2) : "memory");
}
__device__ __forceinline__ void e_tma5d(uint32_t dst, const CUtensorMap* m, uint32_t bar, int c0, int c4) {
  asm volatile(ELECT "cp.async.bulk.tensor.5d.shared::cluster.global.mbarrier::complete_tx::bytes [%0], [%1, {%3,%5,%5,%5,%4}], [%2];\n}\n"
               ::"r"(dst), "l"(m), "r"(bar), "r"(c0), "r"(c4), "r"(0) : "memory");
}
__device__ __forceinline__ void e_bulk(uint32_t dst, const void* src, int bytes, uint32_t bar) {
  asm volatile(ELECT "cp.async.bulk.shared::cluster.global.mbarrier::complete_tx::bytes [%0], [%1], %2, [%3];\n}\n"
               ::"r"(dst), "l"(src), "r"(bytes), "r"(bar) : "memory");
}
__device__ __forceinline__ void e_prefetch(const void* p, int bytes) {
  asm volatile(ELECT "cp.async.bulk.prefetch.L2.global [%0], %1;\n}\n" ::"l"(p), "r"(bytes) : "memory");
}
__device__ __forceinline__ void e_store3d(const CUtensorMap* m, uint32_t src, int c1, int c2) {
  asm volatile(ELECT "cp.async.bulk.tensor.3d.global.shared::cta.bulk_group [%0, {%4,%2,%3}], [%1];\n"
               "@p cp.async.bulk.commit_group;\n@p cp.async.bulk.wait_group.read 0;\n}\n"
               ::"l"(m), "r"(src), "r"(c1), "r"(c2), "r"(0) : "memory");
}
__host__ __device__ constexpr uint64_t mkdesc(uint32_t addr, uint32_t lbo, uint32_t sbo, int swz) {
  return (uint64_t)((addr & 0x3FFFF) >> 4) | ((uint64_t)(lbo >> 4) << 16) | ((uint64_t)(sbo >> 4) << 32) |
         ((uint64_t)swz << 62);
}
#define WG_FENCE() asm volatile("wgmma.fence.sync.aligned;" ::: "memory")
#define WG_COMMIT() asm volatile("wgmma.commit_group.sync.aligned;" ::: "memory")
#define WG_WAIT(n) asm volatile("wgmma.wait_group.sync.aligned " #n ";" ::: "memory")

__device__ __forceinline__ void mma(float& d0, float& d1, float& d2, float& d3, uint32_t a0, uint32_t a1, uint32_t a2,
                                    uint32_t a3, uint32_t b0, uint32_t b1) {
  asm volatile("mma.sync.aligned.m16n8k16.row.col.f32.bf16.bf16.f32 {%0,%1,%2,%3},{%4,%5,%6,%7},{%8,%9},{%0,%1,%2,%3};"
               : "+f"(d0), "+f"(d1), "+f"(d2), "+f"(d3)
               : "r"(a0), "r"(a1), "r"(a2), "r"(a3), "r"(b0), "r"(b1));
}
__device__ __forceinline__ void mmac(float (&d)[4], uint32_t a0, uint32_t a1, uint32_t a2, uint32_t a3, uint32_t b0,
                                     uint32_t b1, const float (&c)[4]) {
  asm volatile("mma.sync.aligned.m16n8k16.row.col.f32.bf16.bf16.f32 {%0,%1,%2,%3},{%4,%5,%6,%7},{%8,%9},{%10,%11,%12,%13};"
               : "=f"(d[0]), "=f"(d[1]), "=f"(d[2]), "=f"(d[3])
               : "r"(a0), "r"(a1), "r"(a2), "r"(a3), "r"(b0), "r"(b1), "f"(c[0]), "f"(c[1]), "f"(c[2]), "f"(c[3]));
}
__device__ __forceinline__ void mma_p(int p, float (&d)[4], uint32_t a0, uint32_t a1, uint32_t a2, uint32_t a3, uint32_t b0, uint32_t b1) {
  asm volatile("{\n.reg .pred q;\nsetp.ne.b32 q, %10, 0;\n"
               "@q mma.sync.aligned.m16n8k16.row.col.f32.bf16.bf16.f32 {%0,%1,%2,%3},{%4,%5,%6,%7},{%8,%9},{%0,%1,%2,%3};\n}\n"
               : "+f"(d[0]), "+f"(d[1]), "+f"(d[2]), "+f"(d[3])
               : "r"(a0), "r"(a1), "r"(a2), "r"(a3), "r"(b0), "r"(b1), "r"(p));
}
__device__ __forceinline__ void mmac_p(int p, float (&d)[4], uint32_t a0, uint32_t a1, uint32_t a2, uint32_t a3, uint32_t b0,
                                       uint32_t b1, const float (&c)[4]) {
  asm volatile("{\n.reg .pred q;\nsetp.ne.b32 q, %14, 0;\n"
               "@q mma.sync.aligned.m16n8k16.row.col.f32.bf16.bf16.f32 {%0,%1,%2,%3},{%4,%5,%6,%7},{%8,%9},{%10,%11,%12,%13};\n}\n"
               : "+f"(d[0]), "+f"(d[1]), "+f"(d[2]), "+f"(d[3])
               : "r"(a0), "r"(a1), "r"(a2), "r"(a3), "r"(b0), "r"(b1), "f"(c[0]), "f"(c[1]), "f"(c[2]), "f"(c[3]), "r"(p));
}
__device__ __forceinline__ void mma_k8(float (&d)[4], uint32_t a0, uint32_t a1, uint32_t b0) {
  asm volatile("mma.sync.aligned.m16n8k8.row.col.f32.bf16.bf16.f32 {%0,%1,%2,%3},{%4,%5},{%6},{%0,%1,%2,%3};"
               : "+f"(d[0]), "+f"(d[1]), "+f"(d[2]), "+f"(d[3]) : "r"(a0), "r"(a1), "r"(b0));
}
__device__ __forceinline__ void mma0(float& d0, float& d1, float& d2, float& d3, uint32_t a0, uint32_t a1, uint32_t a2,
                                     uint32_t a3, uint32_t b0, uint32_t b1) {
  asm volatile("mma.sync.aligned.m16n8k16.row.col.f32.bf16.bf16.f32 {%0,%1,%2,%3},{%4,%5,%6,%7},{%8,%9},{%10,%10,%10,%10};"
               : "=f"(d0), "=f"(d1), "=f"(d2), "=f"(d3)
               : "r"(a0), "r"(a1), "r"(a2), "r"(a3), "r"(b0), "r"(b1), "f"(0.f));
}
__device__ __forceinline__ uint32_t pack_bf(float lo, float hi) {
  uint32_t r;
  asm("cvt.rn.bf16x2.f32 %0, %1, %2;" : "=r"(r) : "f"(hi), "f"(lo));
  return r;
}
__device__ __forceinline__ float bf_lo(uint32_t w) { return __uint_as_float(w << 16); }
__device__ __forceinline__ float bf_hi(uint32_t w) { return __uint_as_float(w & 0xffff0000u); }
__device__ __forceinline__ float bf_round(float x) { return __bfloat162float(__float2bfloat16_rn(x)); }
__device__ __forceinline__ uint32_t bmax2(uint32_t a, uint32_t b) {
  uint32_t r; asm("max.bf16x2 %0, %1, %2;" : "=r"(r) : "r"(a), "r"(b)); return r;
}
__device__ __forceinline__ uint32_t bmin2(uint32_t a, uint32_t b) {
  uint32_t r; asm("min.bf16x2 %0, %1, %2;" : "=r"(r) : "r"(a), "r"(b)); return r;
}
__device__ __forceinline__ float ex2(float x) { float r; asm("ex2.approx.ftz.f32 %0, %1;" : "=f"(r) : "f"(x)); return r; }
__device__ __forceinline__ float rcp(float x) { float r; asm("rcp.approx.ftz.f32 %0, %1;" : "=f"(r) : "f"(x)); return r; }
__device__ __forceinline__ void ldsm4(uint32_t (&r)[4], uint32_t a) {
  asm volatile("ldmatrix.sync.aligned.m8n8.x4.shared.b16 {%0,%1,%2,%3}, [%4];"
               : "=r"(r[0]), "=r"(r[1]), "=r"(r[2]), "=r"(r[3]) : "r"(a) : "memory");
}
__device__ __forceinline__ void ldsm4t(uint32_t (&r)[4], uint32_t a) {
  asm volatile("ldmatrix.sync.aligned.m8n8.x4.trans.shared.b16 {%0,%1,%2,%3}, [%4];"
               : "=r"(r[0]), "=r"(r[1]), "=r"(r[2]), "=r"(r[3]) : "r"(a) : "memory");
}
__device__ __forceinline__ void stsm4(uint32_t a, uint32_t r0, uint32_t r1, uint32_t r2, uint32_t r3) {
  asm volatile("stmatrix.sync.aligned.m8n8.x4.shared.b16 [%0], {%1,%2,%3,%4};"
               ::"r"(a), "r"(r0), "r"(r1), "r"(r2), "r"(r3) : "memory");
}
__device__ __forceinline__ uint32_t lds32(uint32_t a) {
  uint32_t r; asm volatile("ld.shared.u32 %0, [%1];" : "=r"(r) : "r"(a) : "memory"); return r;
}
__device__ __forceinline__ uint32_t lds16(uint32_t a) {
  uint32_t r; asm volatile("{\n.reg .u16 h;\nld.shared.u16 h, [%1];\ncvt.u32.u16 %0, h;\n}\n" : "=r"(r) : "r"(a) : "memory"); return r;
}
__device__ __forceinline__ uint2 lds64(uint32_t a) {
  uint2 r; asm volatile("ld.shared.v2.u32 {%0,%1}, [%2];" : "=r"(r.x), "=r"(r.y) : "r"(a) : "memory"); return r;
}
__device__ __forceinline__ uint4 lds128(uint32_t a) {
  uint4 r;
  asm volatile("ld.shared.v4.u32 {%0,%1,%2,%3}, [%4];" : "=r"(r.x), "=r"(r.y), "=r"(r.z), "=r"(r.w) : "r"(a) : "memory");
  return r;
}
__device__ __forceinline__ void sts32(uint32_t a, uint32_t v) { asm volatile("st.shared.u32 [%0], %1;" ::"r"(a), "r"(v) : "memory"); }
__device__ __forceinline__ void sts16(uint32_t a, uint32_t v) {
  asm volatile("{\n.reg .u16 h;\ncvt.u16.u32 h, %1;\nst.shared.u16 [%0], h;\n}\n" ::"r"(a), "r"(v) : "memory");
}
__device__ __forceinline__ void sts64(uint32_t a, uint32_t x, uint32_t y) {
  asm volatile("st.shared.v2.u32 [%0], {%1,%2};" ::"r"(a), "r"(x), "r"(y) : "memory");
}
__device__ __forceinline__ void sts128(uint32_t a, uint32_t x, uint32_t y, uint32_t z, uint32_t w) {
  asm volatile("st.shared.v4.u32 [%0], {%1,%2,%3,%4};" ::"r"(a), "r"(x), "r"(y), "r"(z), "r"(w) : "memory");
}
__device__ __forceinline__ uint4 ld_x(const uint4* p) {
  uint4 r;
  asm volatile("{\n.reg .b128 t;\nld.relaxed.gpu.global.b128 t, [%4];\nmov.b128 {%0,%1,%2,%3}, t;\n}\n"
               : "=r"(r.x), "=r"(r.y), "=r"(r.z), "=r"(r.w) : "l"(p) : "memory");
  return r;
}
__device__ __forceinline__ uint32_t ld_x32(const uint32_t* p) {
  uint32_t r; asm volatile("ld.relaxed.gpu.global.u32 %0, [%1];" : "=r"(r) : "l"(p) : "memory"); return r;
}
__device__ __forceinline__ void st_x(uint4* p, uint32_t x, uint32_t y, uint32_t z, uint32_t w) {
  asm volatile("{\n.reg .b128 t;\nmov.b128 t, {%1,%2,%3,%4};\nst.relaxed.gpu.global.b128 [%0], t;\n}\n"
               ::"l"(p), "r"(x), "r"(y), "r"(z), "r"(w) : "memory");
}
__device__ __forceinline__ void st_x_p(int p, uint4* a, uint32_t x, uint32_t y, uint32_t z, uint32_t w) {
  asm volatile("{\n.reg .b128 t;\n.reg .pred q;\nsetp.ne.b32 q, %5, 0;\nmov.b128 t, {%1,%2,%3,%4};\n@q st.relaxed.gpu.global.b128 [%0], t;\n}\n"
               ::"l"(a), "r"(x), "r"(y), "r"(z), "r"(w), "r"(p) : "memory");
}
__device__ __forceinline__ void sts64_p(int p, uint32_t a, uint32_t x, uint32_t y) {
  asm volatile("{\n.reg .pred q;\nsetp.ne.b32 q, %3, 0;\n@q st.shared.v2.u32 [%0], {%1,%2};\n}\n" ::"r"(a), "r"(x), "r"(y), "r"(p) : "memory");
}
__device__ __forceinline__ void st_x32(uint32_t* p, uint32_t x) {
  asm volatile("st.relaxed.gpu.global.u32 [%0], %1;" ::"l"(p), "r"(x) : "memory");
}
__device__ __forceinline__ uint32_t nz(uint32_t w) { return max(w, 1u); }
__device__ __forceinline__ uint32_t fu(float x) { return __float_as_uint(x); }
__device__ __forceinline__ float uf(uint32_t x) { return __uint_as_float(x); }

__device__ __forceinline__ void wgmma_ss_n96(float (&d)[48], uint64_t da, uint64_t db, int sc) {
  asm volatile("{\n.reg .pred p;\nsetp.ne.b32 p, %50, 0;\n"
      "wgmma.mma_async.sync.aligned.m64n96k16.f32.bf16.bf16 "
      "{%0,%1,%2,%3,%4,%5,%6,%7,%8,%9,%10,%11,%12,%13,%14,%15,%16,%17,%18,%19,%20,%21,%22,%23,%24,%25,%26,%27,%28,%29,%30,%31,%32,%33,%34,%35,%36,%37,%38,%39,%40,%41,%42,%43,%44,%45,%46,%47}, "
      "%48, %49, p, 1, 1, 0, 1;\n}\n"
      : "+f"(d[0]), "+f"(d[1]), "+f"(d[2]), "+f"(d[3]), "+f"(d[4]), "+f"(d[5]), "+f"(d[6]), "+f"(d[7]),
        "+f"(d[8]), "+f"(d[9]), "+f"(d[10]), "+f"(d[11]), "+f"(d[12]), "+f"(d[13]), "+f"(d[14]), "+f"(d[15]),
        "+f"(d[16]), "+f"(d[17]), "+f"(d[18]), "+f"(d[19]), "+f"(d[20]), "+f"(d[21]), "+f"(d[22]), "+f"(d[23]),
        "+f"(d[24]), "+f"(d[25]), "+f"(d[26]), "+f"(d[27]), "+f"(d[28]), "+f"(d[29]), "+f"(d[30]), "+f"(d[31]),
        "+f"(d[32]), "+f"(d[33]), "+f"(d[34]), "+f"(d[35]), "+f"(d[36]), "+f"(d[37]), "+f"(d[38]), "+f"(d[39]),
        "+f"(d[40]), "+f"(d[41]), "+f"(d[42]), "+f"(d[43]), "+f"(d[44]), "+f"(d[45]), "+f"(d[46]), "+f"(d[47])
      : "l"(da), "l"(db), "r"(sc));
}

__device__ __forceinline__ void wgmma_ss_n128(float (&d)[64], uint64_t da, uint64_t db, int sc) {
  asm volatile("{\n.reg .pred p;\nsetp.ne.b32 p, %66, 0;\n"
      "wgmma.mma_async.sync.aligned.m64n128k16.f32.bf16.bf16 "
      "{%0,%1,%2,%3,%4,%5,%6,%7,%8,%9,%10,%11,%12,%13,%14,%15,%16,%17,%18,%19,%20,%21,%22,%23,%24,%25,%26,%27,%28,%29,%30,%31,%32,%33,%34,%35,%36,%37,%38,%39,%40,%41,%42,%43,%44,%45,%46,%47,%48,%49,%50,%51,%52,%53,%54,%55,%56,%57,%58,%59,%60,%61,%62,%63}, "
      "%64, %65, p, 1, 1, 0, 1;\n}\n"
      : "+f"(d[0]), "+f"(d[1]), "+f"(d[2]), "+f"(d[3]), "+f"(d[4]), "+f"(d[5]), "+f"(d[6]), "+f"(d[7]),
        "+f"(d[8]), "+f"(d[9]), "+f"(d[10]), "+f"(d[11]), "+f"(d[12]), "+f"(d[13]), "+f"(d[14]), "+f"(d[15]),
        "+f"(d[16]), "+f"(d[17]), "+f"(d[18]), "+f"(d[19]), "+f"(d[20]), "+f"(d[21]), "+f"(d[22]), "+f"(d[23]),
        "+f"(d[24]), "+f"(d[25]), "+f"(d[26]), "+f"(d[27]), "+f"(d[28]), "+f"(d[29]), "+f"(d[30]), "+f"(d[31]),
        "+f"(d[32]), "+f"(d[33]), "+f"(d[34]), "+f"(d[35]), "+f"(d[36]), "+f"(d[37]), "+f"(d[38]), "+f"(d[39]),
        "+f"(d[40]), "+f"(d[41]), "+f"(d[42]), "+f"(d[43]), "+f"(d[44]), "+f"(d[45]), "+f"(d[46]), "+f"(d[47]),
        "+f"(d[48]), "+f"(d[49]), "+f"(d[50]), "+f"(d[51]), "+f"(d[52]), "+f"(d[53]), "+f"(d[54]), "+f"(d[55]),
        "+f"(d[56]), "+f"(d[57]), "+f"(d[58]), "+f"(d[59]), "+f"(d[60]), "+f"(d[61]), "+f"(d[62]), "+f"(d[63])
      : "l"(da), "l"(db), "r"(sc));
}

struct Params {
  const __nv_bfloat16 *logA, *Aim, *Cre, *Cim, *logdt, *Dskip, *x, *wphi, *wo;
  __nv_bfloat16* out;
  uint4* xs;
  long long* ts;
};

__device__ __forceinline__ uint4 tr_row(const uint4 (&v)[8], int i) {
  uint32_t o[4];
#pragma unroll
  for (int m = 0; m < 4; m++) {
    const uint4 &ra = v[2 * m], &rb = v[2 * m + 1];
    const int k = i >> 1;
    const uint32_t xa = k == 0 ? ra.x : k == 1 ? ra.y : k == 2 ? ra.z : ra.w;
    const uint32_t xb = k == 0 ? rb.x : k == 1 ? rb.y : k == 2 ? rb.z : rb.w;
    o[m] = __byte_perm(xa, xb, (i & 1) ? 0x7632 : 0x5410);
  }
  return make_uint4(o[0], o[1], o[2], o[3]);
}

struct cpx { float r, i; };
__device__ __forceinline__ cpx cmul(cpx a, cpx b) { return {a.r * b.r - a.i * b.i, a.r * b.i + a.i * b.r}; }
__device__ __forceinline__ cpx csq(cpx a) { return {a.r * a.r - a.i * a.i, 2.f * (a.r * a.i)}; }
__device__ __forceinline__ cpx polar(float e, float t) {
  const float m = ex2(e);
  return {m * __cosf(t), m * __sinf(t)};
}

struct KgenRaw { unsigned short la, ai, cr, ci, ldt; };
__device__ __forceinline__ KgenRaw kgen_load(const Params& P, int d, int unit, int lane) {
  const int o = d * 128 + unit * 32 + lane;
  return {__ldg((const unsigned short*)P.logA + o), __ldg((const unsigned short*)P.Aim + o), __ldg((const unsigned short*)P.Cre + o),
          __ldg((const unsigned short*)P.Cim + o), __ldg((const unsigned short*)P.logdt + d)};
}
__device__ __forceinline__ void kgen_unit(const KgenRaw& r, int lane, uint32_t buf, uint32_t open_bar, float& dt,
                                          float (&k)[5][4], float& k2048) {
  dt = bf_round(expf(bf_lo(r.ldt)));
  const float a2 = -(bf_round(expf(bf_lo(r.la))) * dt) * 1.4426950408889634f;
  const float f = bf_lo(r.ai) * dt;
  const float r128 = f * 20.371832715762604f;
  const cpx C = {bf_lo(r.cr), -bf_lo(r.ci)};
  const uint32_t sa = buf + (lane & 7) * 128 + ((((lane >> 3) ^ lane) & 7) << 4);
  const uint32_t lb = buf + (lane >> 3) * 128 + (((lane ^ (lane >> 3)) & 7) << 4);
  const uint32_t la = buf + ((lane >> 3) & 1) * 1024 + (lane >> 4) * 128 + (((lane ^ (lane >> 4)) & 7) << 4);
  auto put = [&](const cpx (&v)[8], uint32_t off) {
    stsm4(sa + off, pack_bf(v[0].r, v[0].i), pack_bf(v[1].r, v[1].i), pack_bf(v[2].r, v[2].i), pack_bf(v[3].r, v[3].i));
    stsm4((sa ^ 64) + off, pack_bf(v[4].r, v[4].i), pack_bf(v[5].r, v[5].i), pack_bf(v[6].r, v[6].i), pack_bf(v[7].r, v[7].i));
  };
  uint32_t A[4][4], B[5][2][4];
  auto getB = [&](int j, uint32_t off) {
    __syncwarp();
    ldsm4(B[j][0], lb + off);
    ldsm4(B[j][1], (lb ^ 64) + 512 + off);
  };
  cpx t0[8], t1[8], t2[8], t3[8], t4[8];
  t0[0] = {1.f, 0.f};
  t0[1] = polar(a2, f);
  t1[0] = polar(a2 * 128.f, (r128 - rintf(r128)) * 6.283185307179586f);
  t0[2] = csq(t0[1]); t0[4] = csq(t0[2]);
  t2[0] = csq(t1[0]); t3[0] = csq(t2[0]); t4[0] = csq(t3[0]);
  t0[3] = cmul(t0[2], t0[1]); t0[5] = cmul(t0[4], t0[1]); t0[6] = cmul(t0[4], t0[2]); t0[7] = cmul(t0[4], t0[3]);
  put(t0, 0); getB(0, 0);
  {
    cpx w8 = csq(t0[4]);
    w8.i = -w8.i;
    const cpx w16 = csq(w8), w32 = csq(w16), w64 = csq(w32);
    cpx a[8];
    a[0] = C; a[1] = cmul(C, w8);
    a[2] = cmul(a[0], w16); a[3] = cmul(a[1], w16);
#pragma unroll
    for (int i = 0; i < 4; i++) a[4 + i] = cmul(a[i], w32);
    put(a, 0);
#pragma unroll
    for (int i = 0; i < 8; i++) a[i] = cmul(a[i], w64);
    put(a, 1024);
    __syncwarp();
#pragma unroll
    for (int s = 0; s < 4; s++) ldsm4(A[s], (la ^ (s << 5)) + s * 256);
  }
#pragma unroll
  for (int i = 1; i < 8; i++) t1[i] = cmul(t0[i], t1[0]);
  put(t1, 0); getB(1, 0);
#pragma unroll
  for (int i = 1; i < 8; i++) t2[i] = cmul((i & 1) ? t1[i & 6] : t0[i & 6], t2[0]);
  put(t2, 1024); getB(2, 1024);
#pragma unroll
  for (int i = 1; i < 8; i++) t3[i] = cmul((i & 2) ? t2[i & 5] : ((i & 1) ? t1[i & 4] : t0[i & 4]), t3[0]);
  put(t3, 0); getB(3, 0);
#pragma unroll
  for (int i = 1; i < 8; i++) t4[i] = cmul((i & 4) ? t3[i & 3] : ((i & 2) ? t2[i & 1] : t1[0]), t4[0]);
  put(t4, 1024); getB(4, 1024);
  const cpx we = csq(t4[0]);
  k2048 += C.r * we.r + C.i * we.i;
  if (open_bar) mbar_wait(open_bar);
#pragma unroll
  for (int s = 0; s < 4; s++)
#pragma unroll
    for (int j = 0; j < 5; j++)
      mma(k[j][0], k[j][1], k[j][2], k[j][3], A[s][0], A[s][1], A[s][2], A[s][3], B[j][s >> 1][2 * (s & 1)], B[j][s >> 1][2 * (s & 1) + 1]);
}

__device__ __forceinline__ void build_tables(uint32_t tb, int lane, float (&k)[5][4], float k2048) {
  const int g = lane >> 2, c = lane & 3;
  const uint32_t kc = tb + T_KC + 16;
  {
    const uint32_t a0 = kc + 16 * g + 4 * c, a2 = kc + 2 * (256 + 4 * g + c);
    const uint32_t a3 = kc + 2 * (384 + 2 * g + 64 * (c & 1) + (c >> 1)), a4 = kc + 2 * (512 + g + 32 * c);
#pragma unroll
    for (int r = 0; r < 2; r++) {
      sts32(a0 + 128 * r, pack_bf(k[0][2 * r], k[0][2 * r + 1]));
      sts32(a0 + 128 * r + 256, pack_bf(k[1][2 * r], k[1][2 * r + 1]));
      const uint32_t w2 = pack_bf(k[2][2 * r], k[2][2 * r + 1]);
      const uint32_t w3 = pack_bf(k[3][2 * r], k[3][2 * r + 1]);
      const uint32_t w4 = pack_bf(k[4][2 * r], k[4][2 * r + 1]);
      sts16(a2 + 64 * r, w2); sts16(a2 + 64 * r + 128, w2 >> 16);
      sts16(a3 + 32 * r, w3); sts16(a3 + 32 * r + 64, w3 >> 16);
      sts16(a4 + 16 * r, w4); sts16(a4 + 16 * r + 32, w4 >> 16);
    }
  }
  if (lane == 0) { sts16(kc + 2 * 640, pack_bf(k2048, 0.f)); sts16(kc - 2, 0); }
  __syncwarp();
  const uint32_t td = tb + T_D + 32;
  {
    const uint4 v = lds128(kc + 16 * lane);
    const uint32_t pv = lds16(kc + 16 * lane - 2);
    sts128(td + 32 * lane, __byte_perm(v.x, pv, 0x5410), __byte_perm(v.x, v.x, 0x1032), __byte_perm(v.y, v.x, 0x7610),
           __byte_perm(v.y, v.y, 0x1032));
    sts128(td + 32 * lane + 16, __byte_perm(v.z, v.y, 0x7610), __byte_perm(v.z, v.z, 0x1032),
           __byte_perm(v.w, v.z, 0x7610), __byte_perm(v.w, v.w, 0x1032));
  }
  {
    const uint2 v = lds64(kc + 512 + 8 * lane);
    const uint32_t k4 = lds16(kc + 512 + 8 * lane + 8);
    const uint32_t pv = lds16(kc + (lane == 0 ? 510 : 512 + 8 * lane));
    const uint32_t k22 = __byte_perm(v.y, v.y, 0x1010);
    sts128(td + 1024 + 32 * lane, __byte_perm(v.x, pv, 0x5410), __byte_perm(v.x, v.x, 0x1010),
           __byte_perm(v.x, v.x, 0x1032), __byte_perm(v.y, v.x, 0x7610));
    sts128(td + 1024 + 32 * lane + 16, k22, k22, __byte_perm(v.y, v.y, 0x1032), __byte_perm(k4, v.y, 0x7610));
  }
  {
    const uint32_t kk = lds16(kc + 2 * 384);
    const uint32_t w = lane < 3 ? (kk | (kk << 16)) : (lane == 3 ? (kk << 16) : 0u);
    if (lane < 24) sts32(td + 4 * (lane < 16 ? 512 + lane : lane - 24), w);
    const uint32_t lo_ = lds16(kc + 2 * 511), le_ = lds16(kc + 2 * 512);
    const uint32_t ja = tb + T_5 + (lane < 16 ? 4 * lane : 256 + 4 * lane);
    sts32(ja, lane == 16 ? (le_ << 16) : 0u);
    sts32(ja + 384, lane == 16 ? (lo_ << 16) : 0u);
    sts32(tb + (lane < 16 ? T_7 : T_9 - 64) + 4 * lane, 0u);
  }
#pragma unroll
  for (int s = 0; s < 2; s++) {
    const uint32_t b = kc + 2 * (s ? 512 : 384) + 8 * lane;
    const uint2 v = lds64(b);
    uint32_t em = lds16(b - 2), e0 = v.x;
    const uint32_t e4 = lds16(b + 8);
    if (lane == 0) { em = 0; e0 = 0; }
    sts64(tb + (s ? T_7 : T_3) + 64 + 8 * lane, __byte_perm(v.x, em, 0x5432), __byte_perm(v.y, v.x, 0x7632));
    sts64(tb + (s ? T_9 : T_5) + 64 + 8 * lane, __byte_perm(v.y, e0, 0x5410), __byte_perm(e4, v.y, 0x5410));
  }
  __syncwarp();
}

__device__ __forceinline__ uint32_t box2w(int lo, int n, int o) {
  return ((unsigned)(o - lo) < (unsigned)n ? 0x3F80u : 0u) | ((unsigned)(o + 1 - lo) < (unsigned)n ? 0x3F800000u : 0u);
}

__device__ __forceinline__ void conv_channel(uint32_t ub, uint32_t tb, int lane, uint4* ydst) {
  const int g = lane >> 2, c = lane & 3, x = g - 2 * c;
  const uint32_t st = tb + T_ST + lane * 8;
  const int mi = lane >> 3;
  const uint32_t qa = ub + U_PAD + 16 * (lane & 7) + ((mi == 0 || mi == 3) ? U_ODD : 0) - (mi == 0 ? 16 : 0);
  const uint32_t kv = lds16(tb + T_KC + 16 + 2 * 512);
  {
    const uint32_t hb = ub + U_PAD + (mi & 1) * U_ODD + 16 * ((lane >> 4) + (lane & 7)) - 16;
    const int oh = c < 2 ? 8 + 2 * c : 2 * c - 8;
    const uint32_t bx0 = box2w(g - 4, 9, 2 * c), bx1 = box2w(g - 3, 7, 2 * c), bx2 = box2w(g - 4, 9, oh), bx3 = box2w(g - 3, 7, oh);
    uint32_t f7[9], f9a[9], f9b[9];
    const uint32_t fa = tb + T_7 + 4 * (8 + x);
#pragma unroll
    for (int m = 0; m < 9; m++) {
      f7[m] = lds32(fa + 32 * m);
      f9b[m] = lds32(fa + 320 + 32 * m);
      f9a[m] = lds32(fa + 316 + 32 * m);
    }
    mbar_wait(BAR(MB_EMPTY + 15));
    TS(36);
    uint32_t z09[8], z07[8], zm9[8], zm7[8];
#pragma unroll
    for (int i = 0; i < 8; i++) {
      uint32_t h[4];
      ldsm4(h, hb + 128 * i);
      float y0, y1, y2, y3, w0, w1, w2, w3;
      mma0(y0, y1, y2, y3, bx0, bx1, bx2, bx3, h[2], c < 2 ? h[3] : h[1]);
      mma0(w0, w1, w2, w3, bx0, bx1, bx2, bx3, h[1], c < 2 ? h[2] : h[0]);
      z09[i] = pack_bf(y0, y1); z07[i] = pack_bf(y2, y3);
      zm9[i] = pack_bf(w0, w1); zm7[i] = pack_bf(w2, w3);
    }
    float a[4][2][4];
#pragma unroll
    for (int kap = 0; kap < 4; kap++)
#pragma unroll
      for (int sg = 0; sg < 2; sg++)
#pragma unroll
        for (int bk = 3; bk >= kap; bk--) {
          const int m = 2 * (bk - kap) + 1;
          float(&a0)[4] = a[bk][0];
          float(&a1)[4] = a[bk][1];
          if (sg == 0 && kap == 0) {
            mma0(a0[0], a0[1], a0[2], a0[3], f9a[m], f9a[m + 1], f9a[m - 1], f9a[m], z09[0], z09[1]);
            mma0(a1[0], a1[1], a1[2], a1[3], f9b[m], f9b[m + 1], f9b[m - 1], f9b[m], zm9[0], zm9[1]);
          } else if (sg == 0) {
            mma(a0[0], a0[1], a0[2], a0[3], f9a[m], f9a[m + 1], f9a[m - 1], f9a[m], z09[2 * kap], z09[2 * kap + 1]);
            mma(a1[0], a1[1], a1[2], a1[3], f9b[m], f9b[m + 1], f9b[m - 1], f9b[m], zm9[2 * kap], zm9[2 * kap + 1]);
          } else {
            mma(a0[0], a0[1], a0[2], a0[3], f7[m], f7[m + 1], f7[m - 1], f7[m], zm7[2 * kap], zm7[2 * kap + 1]);
            mma(a1[0], a1[1], a1[2], a1[3], f7[m], f7[m + 1], f7[m - 1], f7[m], z07[2 * kap], z07[2 * kap + 1]);
          }
        }
#pragma unroll
    for (int bk = 0; bk < 4; bk++) {
      sts64(st + 256 * (8 + 2 * bk), pack_bf(a[bk][0][0], a[bk][0][1]), pack_bf(a[bk][1][0], a[bk][1][1]));
      sts64(st + 256 * (9 + 2 * bk), pack_bf(a[bk][0][2], a[bk][0][3]), pack_bf(a[bk][1][2], a[bk][1][3]));
    }
  }
  TS(44);
  {
    const int oh = c < 3 ? 2 * c : -10;
    const uint32_t bx0 = box2w(g - 10, 5, 2 * c - 8), bx1 = box2w(g - 5, 3, 2 * c - 8), bx2 = box2w(g - 10, 5, oh), bx3 = box2w(g - 5, 3, oh);
    const uint32_t lb0 = ((unsigned)(x + 5) < 2u ? kv : 0u) | ((unsigned)(x + 4) < 2u ? kv << 16 : 0u);
    const uint32_t lb1 = ((unsigned)(x - 3) < 2u ? kv : 0u) | ((unsigned)(x - 4) < 2u ? kv << 16 : 0u);
    const int q0 = g - 1, q1 = c < 3 ? g : g - 2;
    uint32_t y0a = ub + U_PAD + (q0 & 1) * U_ODD + 16 * (q0 >> 1) + 4 * c;
    uint32_t y1a = ub + U_PAD + (q1 & 1) * U_ODD + 16 * (q1 >> 1) + 4 * c;
    uint2 a5[10], a3[10];
    const uint32_t aa = tb + T_5 + 4 * (8 + 2 * g - 2 * c);
#pragma unroll
    for (int m = 0; m < 10; m++) { a5[m] = lds64(aa + 32 * m); a3[m] = lds64(aa + 384 + 32 * m); }
    float T[6][4];
#pragma unroll
    for (int i = 0; i < 6; i++) T[i][0] = T[i][1] = T[i][2] = T[i][3] = 0.f;
    uint32_t x5[2] = {0, 0}, x3[2] = {0, 0}, yb[4], lq[4];
    uint32_t lqa = qa, sta = st + 256 * 8;
    uint2 sv;
    auto fetch = [&]() {
      yb[0] = lds32(y0a); yb[1] = lds32(y1a); yb[2] = lds32(y0a + 64); yb[3] = lds32(y1a + 64);
      ldsm4(lq, lqa);
      sv = lds64(min(sta, st + 256 * 15));
      y0a += 128; y1a += 128; lqa += 128; sta += 256;
    };
    fetch();
#pragma unroll 2
    for (int kap = -1; kap < 13; kap++) {
      float yn[2][4];
      mma0(yn[0][0], yn[0][1], yn[0][2], yn[0][3], bx0, bx1, bx2, bx3, yb[0], yb[1]);
      mma0(yn[1][0], yn[1][1], yn[1][2], yn[1][3], bx0, bx1, bx2, bx3, yb[2], yb[3]);
      sts64_p(kap > 0, sta - 256 * 7, pack_bf(T[0][0], T[0][1]), pack_bf(T[0][2], T[0][3]));
#pragma unroll
      for (int i = 0; i < 5; i++)
        mmac_p((unsigned)kap < 12u - i, T[i], a5[2 * i + 1].x, a5[2 * i + 1].y, a5[2 * i].x, a5[2 * i].y, x5[0], x5[1], T[i + 1]);
      const float ci[4] = {bf_lo(sv.x), bf_hi(sv.x), bf_lo(sv.y), bf_hi(sv.y)};
      mmac_p(kap < 7, T[5], lq[0], lq[1], lq[2], lq[3], lb0, lb1, ci);
      fetch();
#pragma unroll
      for (int i = 0; i < 5; i++)
        mma_p((unsigned)kap < 12u - i, T[i], a3[2 * i + 1].x, a3[2 * i + 1].y, a3[2 * i].x, a3[2 * i].y, x3[0], x3[1]);
#pragma unroll
      for (int hh = 0; hh < 2; hh++) { x5[hh] = pack_bf(yn[hh][0], yn[hh][1]); x3[hh] = pack_bf(yn[hh][2], yn[hh][3]); }
    }
  }
  TS(45);
  {
    uint32_t F[66];
    const uint32_t fa = tb + T_D + 32 + 4 * x;
#pragma unroll
    for (int m = 0; m < 66; m++) F[m] = lds32(fa + 32 * m);
    float T[5][4];
#pragma unroll
    for (int i = 0; i < 5; i++) T[i][0] = T[i][1] = T[i][2] = T[i][3] = 0.f;
    uint32_t qd[8][4], held[2] = {0, 0};
    uint32_t qp = qa + 128 * 15, sta = st + 256 * 14;
    uint4* yd = ydst + 19 * 16;
#pragma unroll
    for (int i = 0; i < 6; i++) ldsm4(qd[i], qp - 16 * i);
    uint2 sv = lds64(sta + 256);
    float ci[4] = {bf_lo(sv.x), bf_hi(sv.x), bf_lo(sv.y), bf_hi(sv.y)};
    TS(46);
#pragma unroll 2
    for (int be = 15; be >= 0; be--) {
#pragma unroll
      for (int k = 4; k >= 1; k--)
        mmac_p(be <= 15 - k, T[k], qd[0][0], qd[0][1], qd[0][2], qd[0][3], F[16 * k + 1], F[16 * k], T[k - 1]);
      mmac(T[0], qd[0][0], qd[0][1], qd[0][2], qd[0][3], F[1], F[0], ci);
      ldsm4(qd[6], qp - 16 * 6);
      ldsm4(qd[7], qp - 16 * 7);
      sv = lds64(sta);
#pragma unroll
      for (int i = 1; i < 8; i++) {
#pragma unroll
        for (int k = 3; k >= 0; k--)
          mma_p(k == 0 || be <= 15 - k, T[k], qd[i][0], qd[i][1], qd[i][2], qd[i][3], F[16 * k + 2 * i + 1], F[16 * k + 2 * i]);
        if (i < 7) ldsm4(qd[i - 1], qp - 128 - 16 * (i - 1));
        if (i == 2) {
          const uint32_t w0 = pack_bf(T[4][0], T[4][1]), w1 = pack_bf(T[4][2], T[4][3]);
          st_x_p(be <= 10 && !(be & 1), yd, nz(w0), w1, held[0], held[1]);
          held[0] = w0; held[1] = w1;
        }
        if (i == 4) {
          if (be <= 4) sv = make_uint2(0, 0);
          ci[0] = bf_lo(sv.x); ci[1] = bf_hi(sv.x); ci[2] = bf_lo(sv.y); ci[3] = bf_hi(sv.y);
        }
      }
      qp -= 128; sta -= 256; yd -= 16;
    }
#pragma unroll
    for (int B = 1; B >= 0; B--)
      st_x(ydst + B * 32, nz(pack_bf(T[2 * B][0], T[2 * B][1])), pack_bf(T[2 * B][2], T[2 * B][3]),
           pack_bf(T[2 * B + 1][0], T[2 * B + 1][1]), pack_bf(T[2 * B + 1][2], T[2 * B + 1][3]));
  }
}

__device__ __forceinline__ void feat(const float (&acc)[48], int j0, const uint32_t (&wf)[4], uint32_t* w) {
  const uint32_t a0 = pack_bf(acc[4 * j0], acc[4 * j0 + 1]), a1 = pack_bf(acc[4 * j0 + 2], acc[4 * j0 + 3]);
  const uint32_t a2 = pack_bf(acc[4 * j0 + 4], acc[4 * j0 + 5]), a3 = pack_bf(acc[4 * j0 + 6], acc[4 * j0 + 7]);
  float p[8];
  mma0(p[0], p[1], p[2], p[3], a0, a1, a2, a3, wf[0], wf[1]);
  mma0(p[4], p[5], p[6], p[7], a0, a1, a2, a3, wf[2], wf[3]);
  w[0] = pack_bf(p[0], p[2]); w[1] = pack_bf(p[1], p[3]); w[2] = pack_bf(p[4], p[6]); w[3] = pack_bf(p[5], p[7]);
}
__device__ __forceinline__ void dual_softmax(const uint32_t* w, uint32_t* e) {
  const float L = 1.44268798828125f;
  uint32_t mx = bmax2(bmax2(w[0], w[1]), bmax2(w[2], w[3]));
  uint32_t mn = bmin2(bmin2(w[0], w[1]), bmin2(w[2], w[3]));
  mx = bmax2(mx, __shfl_xor_sync(0xffffffffu, mx, 1));
  mn = bmin2(mn, __shfl_xor_sync(0xffffffffu, mn, 1));
  mx = bmax2(mx, __shfl_xor_sync(0xffffffffu, mx, 2));
  mn = bmin2(mn, __shfl_xor_sync(0xffffffffu, mn, 2));
  const float mx0 = bf_lo(mx) * -L, mx1 = bf_hi(mx) * -L, mn0 = bf_lo(mn) * L, mn1 = bf_hi(mn) * L;
  float ep[2][4], em[2][4];
#pragma unroll
  for (int i = 0; i < 4; i++) {
    const float x0 = bf_lo(w[i]), x1 = bf_hi(w[i]);
    ep[0][i] = ex2(fmaf(x0, L, mx0)); em[0][i] = ex2(fmaf(x0, -L, mn0));
    ep[1][i] = ex2(fmaf(x1, L, mx1)); em[1][i] = ex2(fmaf(x1, -L, mn1));
  }
  __half2 sp = __floats2half2_rn((ep[0][0] + ep[0][1]) + (ep[0][2] + ep[0][3]), (ep[1][0] + ep[1][1]) + (ep[1][2] + ep[1][3]));
  __half2 sm = __floats2half2_rn((em[0][0] + em[0][1]) + (em[0][2] + em[0][3]), (em[1][0] + em[1][1]) + (em[1][2] + em[1][3]));
  sp = __hadd2(sp, __shfl_xor_sync(0xffffffffu, sp, 1));
  sm = __hadd2(sm, __shfl_xor_sync(0xffffffffu, sm, 1));
  sp = __hadd2(sp, __shfl_xor_sync(0xffffffffu, sp, 2));
  sm = __hadd2(sm, __shfl_xor_sync(0xffffffffu, sm, 2));
  const float rp[2] = {rcp(__low2float(sp)), rcp(__high2float(sp))}, rm[2] = {rcp(__low2float(sm)), rcp(__high2float(sm))};
#pragma unroll
  for (int i = 0; i < 4; i++) {
    const int r = i & 1, k = i & 2;
    e[i] = pack_bf(ep[r][k] * rp[r], ep[r][k + 1] * rp[r]);
    e[4 + i] = pack_bf(em[r][k] * rm[r], em[r][k + 1] * rm[r]);
  }
}

__global__ void __launch_bounds__(NTHREADS, 1)
fused_kernel(const Params P, const __grid_constant__ CUtensorMap mx, const __grid_constant__ CUtensorMap mw,
             const __grid_constant__ CUtensorMap mo, const __grid_constant__ CUtensorMap mu,
             const __grid_constant__ CUtensorMap mout) {
  constexpr uint32_t sb = SB;
  const int tid = threadIdx.x, lane = tid & 31;
  const int warp = __shfl_sync(0xffffffffu, tid >> 5, 0);
  const int b = blockIdx.x, oct = b >> 3, i8 = b & 7;
  const int rt = oct < 8 ? oct : 15 - oct;
  const int hp = (oct >> 3) * 8 + i8;

  const int d = b * 4 + ((tid >> 5) & 3);
  KgenRaw raw = {}, raw3 = {};
  unsigned short dsk = 0;
  if (tid < 384) {
    asm volatile("prefetch.tensormap [%0];" ::"l"(&mu) : "memory");
    asm volatile("prefetch.tensormap [%0];" ::"l"(&mw) : "memory");
    asm volatile("prefetch.tensormap [%0];" ::"l"(&mx) : "memory");
    raw = kgen_load(P, d, tid >> 7, lane);
    raw3 = kgen_load(P, d, 3, lane);
    dsk = __ldg((const unsigned short*)P.Dskip + d);
  }
  if (warp >= 12) asm volatile("setmaxnreg.dec.sync.aligned.u32 32;");
  if (warp == 12) {
    if (lane == 0) {
#pragma unroll
      for (int i = 0; i < 9; i++) mbar_init(BAR(i), 1);
      asm volatile("fence.mbarrier_init.release.cluster;" ::: "memory");
    }
    __syncwarp();
    if (lane < 9) mbar_expect(BAR(0) + 8 * lane, lane == 0 ? 16384 : (lane < 8 ? 28672 : 29696));
    __syncwarp();
    nb_arrive(NB_PREP, 448);
#pragma unroll 1
    for (int kb = 0; kb < 8; kb++) {
      if (kb == STEP_U) e_tma5d(sb + OFF_STG0, &mu, BAR(MB_URAW), i8 * 64, oct * 4);
      e_tma3d(sb + OFF_W + kb * 12288, &mw, BAR(MB_FULL) + 8 * kb, hp * 32, kb * 64, 0);
      if (kb < 5) e_tma2d(sb + OFF_X + (kb < 2 ? kb + 3 : kb - 2) * 16384, &mx, BAR(MB_FULL) + 8 * kb, kb * 64, rt * 256);
    }
    if (smem_u32(smem_raw) != SB) __trap();
  }
  if (warp >= 12) {
    if (warp == 12) {
      nb_sync(NB_PROD, 64);
      e_prefetch(P.x + (size_t)(rt * 256 + hp * 16) * 512, 16384);
      e_bulk(sb + OFF_PHI, P.wphi + hp * 512, 1024, BAR(MB_FULL + 7));
      uint32_t slot = sb + OFF_X + 3 * 16384;
#pragma unroll 1
      for (int n = 0; n < 11; n++) {
        mbar_wait(BAR(MB_EMPTY) + 8 * n);
        const int m = n + 5;
        e_tma2d(slot, &mx, BAR(MB_FULL) + 8 * m, (m & 7) * 64, rt * 256 + (m >> 3) * 128);
        slot = slot == sb + OFF_X + 4 * 16384 ? sb + OFF_X : slot + 16384;
        if (n == 7) e_prefetch(P.wo + (size_t)b * 2048, 4096);
      }
#pragma unroll 1
      for (int i = 0; i < 8; i++) {
        mbar_wait(BAR(MB_EMPTY + 10) + 8 * ((0x54332100u >> (4 * i)) & 7));
        const int w0 = (0x54736210u >> (4 * i)) & 7;
        e_tma3d(sb + OFF_W + w0 * 16384, &mo, BAR(MB_WO), 0, w0 * 64, (hp & 3) * 2);
      }
    } else {
      if (warp == 13) {
        if (lane == 0) {
#pragma unroll
          for (int i = 9; i < 38; i++) mbar_init(BAR(i), i < MB_EMPTY ? 1 : (i < MB_CLOSE ? 4 : 12));
          asm volatile("fence.mbarrier_init.release.cluster;" ::: "memory");
        }
        __syncwarp();
        if (lane < 9) mbar_expect(BAR(MB_FULL + 8) + 8 * lane, lane < 8 ? 16384 : 131072);
        __syncwarp();
        nb_arrive(NB_PROD, 64);
        nb_arrive(NB_PREP, 448);
      }
      nb_sync(NB_ZERO, 96);
      if (warp == 15) {
        mbar_wait(BAR(MB_EMPTY + ZERO_STEP));
        uint4* py = P.xs + X_Y + b * 1024 + lane;
#pragma unroll 1
        for (int i = 0; i < 1024; i += 32) st_x(py + i, 0, 0, 0, 0);
        nb_arrive(NB_YZ, 160);
        nb_arrive(NB_ODONE, 320);
        if (lane == 0) TS1(55);
        return;
      }
      uint32_t* const cnt = (uint32_t*)(P.xs + X_CNT) + (warp == 13 ? i8 : 8 + rt) * 32;
      const unsigned target = (ld_x32(cnt) & ~15u) + 16;
      if (warp == 13) {
        uint4* pp = P.xs + X_PART + (hp * 8 + rt) * 144 + lane;
#pragma unroll 1
        for (int i = 0; i < 144; i += 32) if (i + lane < 144) st_x(pp + i, 0, 0, 0, 0);
      }
      nb_sync(warp == 13 ? NB_INIT : NB_ODONE, warp == 13 ? 160 : 320);
      if (lane == 0) TS1(warp == 13 ? 49 : 56);
      if (lane == 0) asm volatile("red.release.gpu.global.add.u32 [%0], 1;" ::"l"(cnt) : "memory");
      if (lane == 0) TS1(warp == 13 ? 50 : 57);
      const uint32_t* pc = (warp == 13 && (lane & 1)) ? (uint32_t*)(P.xs + X_CNT) + (b >> 4) * 32 : cnt;
#pragma unroll 1
      for (int i = 0; i < SPIN_MAX; i++) {
        unsigned v;
        asm volatile("ld.acquire.gpu.global.u32 %0, [%1];" : "=r"(v) : "l"(pc) : "memory");
        if (__all_sync(0xffffffffu, (int)(v - target) >= 0)) break;
      }
      if (lane == 0) TS1(warp == 13 ? 51 : 58);
      asm volatile("fence.proxy.async;" ::: "memory");
      if (warp == 13) {
        mbar_wait(BAR(MB_EMPTY + 11));
        e_expect(BAR(MB_UFULL), 4 * U_CH);
        e_bulk(sb + OFF_U, P.xs + X_UT + b * (U_CH / 4), 4 * U_CH, BAR(MB_UFULL));
      } else {
        const uint4* src = P.xs + X_O + (rt * 4 + (hp >> 2)) * 4096;
        e_expect(BAR(MB_OA), 47104);
        e_bulk(sb + OFF_X + 32768, src, 32768, BAR(MB_OA));
        e_bulk(sb + OFF_STG0, src + 3200, 14336, BAR(MB_OA));
        nb_sync(NB_BDONE, 288);
        asm volatile("fence.proxy.async.shared::cta;" ::: "memory");
        e_expect(BAR(MB_OB), 18432);
        e_bulk(sb + OFF_U, src + 2048, 18432, BAR(MB_OB));
      }
    }
    return;
  }

  asm volatile("setmaxnreg.inc.sync.aligned.u32 160;");
  const int wg = warp >> 2, w = warp & 3, t = tid & 127;
  const int g = lane >> 2, c = lane & 3;
  const uint32_t tb = sb + OFF_T + w * T_CH;
  {
    float k[5][4], k2048 = 0.f, dt;
#pragma unroll
    for (int j = 0; j < 5; j++) k[j][0] = k[j][1] = k[j][2] = k[j][3] = 0.f;
    const uint32_t kp = tb + (wg & 1) * 2608;
#pragma unroll 1
    for (int r = 0; r <= (wg >> 1); r++) {
      kgen_unit(raw, lane, wg == 2 ? sb + OFF_STG0 + 16384 + w * 2048 : (kp + 127) & ~127u, r ? BAR(MB_EMPTY + 7) : 0u, dt, k, k2048);
      raw = raw3;
      TS(40 + wg + r);
      if (r == 0) {
        if (wg != 2) {
#pragma unroll
          for (int j = 0; j < 5; j++) sts128(kp + j * 512 + lane * 16, fu(k[j][0]), fu(k[j][1]), fu(k[j][2]), fu(k[j][3]));
          k2048 += __shfl_xor_sync(0xffffffffu, k2048, 16);
          k2048 += __shfl_xor_sync(0xffffffffu, k2048, 8);
          if (lane < 8) sts32(kp + 2560 + lane * 4, fu(k2048));
        } else if ((fu(k[0][0]) & fu(k[1][0]) & fu(k[2][0]) & fu(k[3][0]) & fu(k[4][0])) == 0xffffffffu) {
          sts32(kp, 0);
        }
        nb_sync(NB_PREP, 448);
        if (wg == 2) {
#pragma unroll 1
          for (int q = 0; q < 2; q++) {
            const uint32_t src = tb + q * 2608;
#pragma unroll
            for (int j = 0; j < 5; j++) {
              const uint4 v = lds128(src + j * 512 + lane * 16);
              k[j][0] += uf(v.x); k[j][1] += uf(v.y); k[j][2] += uf(v.z); k[j][3] += uf(v.w);
            }
            if (lane < 8) k2048 += uf(lds32(src + 2560 + lane * 4));
          }
        }
      }
    }
    if (wg == 2) {
      if (lane == 0 && (fu(k[0][0]) & fu(k[1][0]) & fu(k[2][0]) & fu(k[3][0]) & fu(k[4][0])) != 0xffffffffu)
        mbar_arrive(BAR(MB_CLOSE));
      TS(34);
#pragma unroll
      for (int o2 = 16; o2; o2 >>= 1) k2048 += __shfl_xor_sync(0xffffffffu, k2048, o2);
      const float sc = 2.f * dt;
#pragma unroll
      for (int j = 0; j < 5; j++) { k[j][0] *= sc; k[j][1] *= sc; k[j][2] *= sc; k[j][3] *= sc; }
      k2048 *= sc;
      if (lane == 0) k[0][0] += bf_lo(dsk);
      build_tables(tb, lane, k, k2048);
      TS(35);
      nb_sync(NB_YZ, 160);
      mbar_wait(BAR(MB_UFULL));
      uint4* const g_y = P.xs + X_Y;
      conv_channel(sb + OFF_U + w * U_CH, tb, lane, g_y + (size_t)d * 256 + lane);
      nb_arrive(NB_BDONE, 288);
      TS(37);
      mbar_wait(BAR(MB_OA));
      const int lam = w * 8 + g;
      const uint4* src = g_y + (size_t)(oct * 32 + c * 8) * 256 + i8 * 32 + lam;
      uint4 v[8];
#pragma unroll 1
      for (int it = 0; it < SPIN_MAX; it++) {
        uint32_t m = 0xffffffffu;
#pragma unroll
        for (int i = 0; i < 8; i++) v[i] = ld_x(src + i * 256);
#pragma unroll
        for (int i = 0; i < 8; i++) m = min(m, v[i].x);
        if (__all_sync(0xffffffffu, m != 0)) break;
      }
      __nv_bfloat16* dst = P.out + (size_t)(i8 * 256 + (lam >> 2) * 16 + (lam & 3) * 2) * 1024 + 512 + oct * 32 + c * 8;
#pragma unroll
      for (int i = 0; i < 8; i++) *(uint4*)(dst + (size_t)((i >> 2) * 128 + ((i >> 1) & 1) * 8 + (i & 1)) * 1024) = tr_row(v, i);
      TS(38);
      GT(63);
      return;
    }
    if (wg == 1) {
      mbar_wait(BAR(MB_URAW));
      TS(48);
      uint4* dst = P.xs + X_UT + (i8 * 64 + g) * (U_CH / 16) + (c & 1) * (U_ODD / 16) + U_PAD / 16 + oct * 8 + w * 2 + (c >> 1);
      uint32_t r[8][4];
#pragma unroll
      for (int i = 0; i < 8; i++) ldsm4t(r[i], sb + OFF_STG0 + w * 4096 + lane * 128 + (((i ^ lane) & 7) << 4));
#pragma unroll
      for (int i = 0; i < 8; i++) dst[i * (U_CH / 2)] = make_uint4(r[i][0], r[i][1], r[i][2], r[i][3]);
      nb_arrive(NB_INIT, 160);
      if (lane == 0) mbar_arrive(BAR(MB_CLOSE));
      mbar_wait(BAR(MB_CLOSE));
    }
    TS(wg * 16 + 1);
  }

  float acc[2][48];
  {
    uint32_t fb = BAR(MB_FULL) + 64 * wg;
    uint32_t da = (uint32_t)mkdesc(sb + OFF_X, 16, 0, 0) + (wg ? 1024 : 3072), db = (uint32_t)mkdesc(sb + OFF_W, 4096, 0, 0);
    constexpr uint64_t ha = mkdesc(0, 0, 1024, 1), hb = mkdesc(0, 0, 512, 2);
#pragma unroll 1
    for (int kb = 0; kb < 8; kb++) {
      mbar_wait(fb);
      if (kb == 0) TS(wg * 16 + 2);
      WG_FENCE();
#pragma unroll
      for (int k = 0; k < 4; k++) {
        wgmma_ss_n96(acc[0], ha | (da + 2 * k), hb | (db + 64 * k), k ? 1 : kb);
        wgmma_ss_n96(acc[1], ha | (da + 2 * k + 512), hb | (db + 64 * k), k ? 1 : kb);
      }
      WG_COMMIT();
      WG_WAIT(1);
      if (kb > 0 && lane == 0) mbar_arrive(fb + 8 * (MB_EMPTY - MB_FULL - 1));
      fb += 8; db += 768;
      da = da == (uint32_t)mkdesc(sb + OFF_X + 65536, 16, 0, 0) ? da - 4096 : da + 1024;
    }
    WG_WAIT(0);
    if (lane == 0) mbar_arrive(fb + 8 * (MB_EMPTY - MB_FULL - 1));
    mbar_wait(fb + 8 * (MB_EMPTY - MB_FULL - 1));
  }
  uint32_t wf[2][4];
  ldsm4t(wf[0], sb + OFF_PHI + (lane & 15) * 32 + (lane >> 4) * 16);
  ldsm4t(wf[1], sb + OFF_PHI + 512 + (lane & 15) * 32 + (lane >> 4) * 16);
  TS(wg * 16 + 3);

  uint32_t pw[32], eq[32];
#pragma unroll
  for (int u = 0; u < 4; u++)
#pragma unroll
    for (int h = 0; h < 2; h++) feat(acc[u & 1], (u < 2 ? 4 : 0) + 2 * h, wf[h], pw + 8 * u + 4 * h);
  {
    uint32_t all = 0xffffffffu;
#pragma unroll
    for (int i = 0; i < 16; i++) all &= pw[2 * i];
    if (wg == 0 && lane == 0 && all != 0xffffffffu) mbar_arrive(BAR(MB_CLOSE));
  }
  mbar_wait(BAR(MB_CLOSE));
  constexpr uint32_t stg0 = sb + OFF_STG0, stg1 = sb + OFF_X + 32768;
  uint32_t sl = (wg ? stg1 : stg0) + w * 3072 + lane * 16;
#pragma unroll
  for (int mt = 0; mt < 2; mt++)
#pragma unroll
    for (int h = 0; h < 2; h++) {
      const float* a = acc[mt] + 32 + 8 * h;
      stsm4(sl + mt * 12288 + 2048 + h * 512, pack_bf(a[0], a[1]), pack_bf(a[2], a[3]), pack_bf(a[4], a[5]), pack_bf(a[6], a[7]));
    }
#pragma unroll 1
  for (int u = 0; u < 4; u++) {
#pragma unroll
    for (int i = 0; i < 16; i++) eq[i] = eq[16 + i];
    dual_softmax(pw, eq + 16);
    dual_softmax(pw + 4, eq + 24);
    if (u < 2) {
#pragma unroll
      for (int i = 0; i < 4; i++) stsm4(sl + i * 512, eq[16 + 4 * i], eq[17 + 4 * i], eq[18 + 4 * i], eq[19 + 4 * i]);
      if (wg) nb_arrive(NB_ST0 + u, 256);
      sl += 12288;
    }
#pragma unroll
    for (int i = 0; i < 24; i++) pw[i] = pw[i + 8];
  }
  TS(wg * 16 + 4);
  uint4* const g_part = P.xs + X_PART;
  uint4* const g_o = P.xs + X_O;
  const uint32_t kvs = stg0;
  if (wg == 0) {
    nb_sync(NB_WG0, 128);
    mbar_wait(BAR(MB_UFULL));
    mbar_wait(BAR(MB_EMPTY + 15));
    float kv[12];
#pragma unroll
    for (int i = 0; i < 12; i++) kv[i] = 0.f;
    const int mi = lane >> 3;
    const uint32_t ao = w * 512 + (lane & 7) * 16 + ((mi & 1) * 2 + (mi >> 1)) * 128, bo = 2048 + (w >> 1) * 512 + lane * 16;
#pragma unroll 1
    for (int j = 0; j < 4; j++) {
      if (j >= 2) nb_sync(NB_ST0 + j - 2, 256);
      const uint32_t sg = (j >= 2 ? stg1 : stg0) + (j & 1) * 12288;
      uint32_t a[4][4], bb[4][4];
#pragma unroll
      for (int s = 0; s < 4; s++) { ldsm4t(a[s], sg + s * 3072 + ao); ldsm4t(bb[s], sg + s * 3072 + bo); }
#pragma unroll
      for (int s = 0; s < 4; s++) {
        mma(kv[0], kv[1], kv[2], kv[3], a[s][0], a[s][1], a[s][2], a[s][3], bb[s][0], bb[s][1]);
        mma(kv[4], kv[5], kv[6], kv[7], a[s][0], a[s][1], a[s][2], a[s][3], bb[s][2], bb[s][3]);
        mma(kv[8], kv[9], kv[10], kv[11], a[s][0], a[s][1], a[s][2], a[s][3], 0x3F803F80u, 0x3F803F80u);
      }
    }
    uint4* pp = g_part + (size_t)(hp * 8 + rt) * 144;
    st_x(pp + t, nz(pack_bf(kv[0], kv[1])), pack_bf(kv[2], kv[3]), pack_bf(kv[4], kv[5]), pack_bf(kv[6], kv[7]));
    if (c < 2) st_x32((uint32_t*)(pp + 128) + w * 16 + c * 8 + g, nz(fu(c ? kv[10] : kv[8])));
    TS(5);
    const uint4* ps = g_part + (size_t)hp * 8 * 144 + t;
    const uint32_t* zs = (const uint32_t*)(g_part + (size_t)(hp * 8 + (lane >> 4) * 4) * 144 + 128) + w * 16 + (lane & 15);
    uint4 v[8];
    uint32_t zv[4];
#pragma unroll 1
    for (int it = 0; it < SPIN_MAX; it++) {
#pragma unroll
      for (int i = 0; i < 8; i++) v[i] = ld_x(ps + i * 144);
#pragma unroll
      for (int i = 0; i < 4; i++) zv[i] = ld_x32(zs + i * 576);
      uint32_t m = min(min(zv[0], zv[1]), min(zv[2], zv[3]));
#pragma unroll
      for (int i = 0; i < 8; i++) m = min(m, v[i].x);
      if (__all_sync(0xffffffffu, m != 0)) break;
    }
    float s4[4][4];
#pragma unroll
    for (int i = 0; i < 4; i++) s4[i][0] = s4[i][1] = s4[i][2] = s4[i][3] = 0.f;
    const uint32_t eye = (g >> 1) == c ? ((g & 1) ? 0x3F800000u : 0x3F80u) : 0u;
#pragma unroll
    for (int r = 0; r < 8; r++) {
      mma_k8(s4[(r & 1) * 2], v[r].x, v[r].y, eye);
      mma_k8(s4[(r & 1) * 2 + 1], v[r].z, v[r].w, eye);
    }
    float s[8];
#pragma unroll
    for (int i = 0; i < 8; i++) s[i] = s4[i >> 2][i & 3] + s4[2 + (i >> 2)][i & 3];
    float zsum = (uf(zv[0]) + uf(zv[1])) + (uf(zv[2]) + uf(zv[3]));
    zsum += __shfl_xor_sync(0xffffffffu, zsum, 16);
    stsm4(kvs + w * 512 + lane * 16, pack_bf(s[0], s[1]), pack_bf(s[2], s[3]), pack_bf(s[4], s[5]), pack_bf(s[6], s[7]));
    if (lane < 16) sts16(kvs + 2048 + (w * 16 + lane) * 2, pack_bf(zsum, 0.f));
    TS(6);
  }
  nb_sync(NB_KV, 256);
  {
    uint32_t kb_[4][4], zb[8];
#pragma unroll
    for (int i = 0; i < 4; i++) ldsm4t(kb_[i], kvs + i * 512 + lane * 16);
#pragma unroll
    for (int i = 0; i < 8; i++) zb[i] = lds32(kvs + 2048 + i * 16 + c * 4);
    uint32_t* od = (uint32_t*)(g_o + (size_t)((rt * 4 + wg * 2) * 32 + hp * 2) * 128) + w * 64 + lane;
#pragma unroll 1
    for (int mt = 0; mt < 2; mt++) {
#pragma unroll
      for (int h = 0; h < 2; h++) {
        const uint32_t* e = eq + 8 * h;
        float n[8], dn[4];
        mma0(dn[0], dn[1], dn[2], dn[3], e[0], e[1], e[2], e[3], zb[4 * h], zb[4 * h + 1]);
        mma0(n[0], n[1], n[2], n[3], e[0], e[1], e[2], e[3], kb_[2 * h][0], kb_[2 * h][1]);
        mma0(n[4], n[5], n[6], n[7], e[0], e[1], e[2], e[3], kb_[2 * h][2], kb_[2 * h][3]);
        mma(dn[0], dn[1], dn[2], dn[3], e[4], e[5], e[6], e[7], zb[4 * h + 2], zb[4 * h + 3]);
        mma(n[0], n[1], n[2], n[3], e[4], e[5], e[6], e[7], kb_[2 * h + 1][0], kb_[2 * h + 1][1]);
        mma(n[4], n[5], n[6], n[7], e[4], e[5], e[6], e[7], kb_[2 * h + 1][2], kb_[2 * h + 1][3]);
        const float r0 = rcp(dn[0] + 1e-6f), r1 = rcp(dn[2] + 1e-6f);
        od[h * 512] = pack_bf(n[0] * r0, n[1] * r0);
        od[h * 512 + 32] = pack_bf(n[2] * r1, n[3] * r1);
        od[h * 512 + 256] = pack_bf(n[4] * r0, n[5] * r0);
        od[h * 512 + 288] = pack_bf(n[6] * r1, n[7] * r1);
      }
#pragma unroll
      for (int i = 0; i < 16; i++) eq[i] = eq[16 + i];
      od += 16384;
    }
  }
  TS(wg * 16 + 7);
  nb_arrive(NB_ODONE, 320);
  if (wg) return;
  mbar_wait(BAR(MB_WO));
  mbar_wait(BAR(MB_OA));
  TS(8);
  nb_sync(NB_BDONE, 288);
  TS(9);
  float oc[64];
  {
    constexpr uint64_t ha = mkdesc(0, 0, 128, 0), hb = mkdesc(0, 0, 1024, 1);
    constexpr uint32_t da0 = (uint32_t)mkdesc(stg1, 1024, 0, 0), db0 = (uint32_t)mkdesc(sb + OFF_W, 8192, 0, 0);
#pragma unroll 1
    for (int j = 0; j < 8; j++) {
      const int kb = (j + 7) & 7;
      if (j == 5) mbar_wait(BAR(MB_OB));
      WG_FENCE();
#pragma unroll
      for (int k = 0; k < 4; k++) wgmma_ss_n128(oc, ha | (da0 + 512 * kb + 128 * k), hb | (db0 + 1024 * kb + 128 * k), k ? 1 : j);
      WG_COMMIT();
    }
    WG_WAIT(0);
  }
  TS(10);
  nb_sync(NB_WG0, 128);
  const uint32_t ot = sb + OFF_W + w * 4096;
#pragma unroll
  for (int i = 0; i < 16; i += 2)
    stsm4(ot + (i >> 3) * 2048 + (lane & 15) * 128 + (((i + (lane >> 4)) ^ lane) & 7) * 16, pack_bf(oc[4 * i], oc[4 * i + 1]),
          pack_bf(oc[4 * i + 2], oc[4 * i + 3]), pack_bf(oc[4 * i + 4], oc[4 * i + 5]), pack_bf(oc[4 * i + 6], oc[4 * i + 7]));
  asm volatile("fence.proxy.async.shared::cta;" ::: "memory");
  __syncwarp();
  e_store3d(&mout, ot, (rt * 4 + (hp >> 2)) * 64 + w * 16, (hp & 3) * 2);
  TS(wg * 16 + 11);
  GT(61 + wg);
}

typedef CUresult (*EncodeFn)(CUtensorMap*, CUtensorMapDataType, cuuint32_t, void*, const cuuint64_t*, const cuuint64_t*,
                             const cuuint32_t*, const cuuint32_t*, CUtensorMapInterleave, CUtensorMapSwizzle,
                             CUtensorMapL2promotion, CUtensorMapFloatOOBfill);

}

extern "C" void kernel_launch(void* const* d_in, const int* in_sizes, int n_in, void* d_out, int out_size) {
  (void)in_sizes; (void)n_in; (void)out_size;
  void* fn = nullptr;
  cudaDriverEntryPointQueryResult qr;
  cudaGetDriverEntryPoint("cuTensorMapEncodeTiled", &fn, cudaEnableDefault, &qr);
  EncodeFn enc = (EncodeFn)fn;
  CUtensorMap mx, mw, mo, mu, mout;
  const cuuint32_t es[5] = {1, 1, 1, 1, 1};
  {
    cuuint64_t dims[2] = {512, 2048}, st[1] = {1024};
    cuuint32_t box[2] = {64, 128};
    enc(&mx, CU_TENSOR_MAP_DATA_TYPE_BFLOAT16, 2, d_in[0], dims, st, box, es, CU_TENSOR_MAP_INTERLEAVE_NONE,
        CU_TENSOR_MAP_SWIZZLE_128B, CU_TENSOR_MAP_L2_PROMOTION_L2_128B, CU_TENSOR_MAP_FLOAT_OOB_FILL_NONE);
  }
  {
    cuuint64_t dims[3] = {512, 512, 3}, st[2] = {3072, 1024};
    cuuint32_t box[3] = {32, 64, 3};
    enc(&mw, CU_TENSOR_MAP_DATA_TYPE_BFLOAT16, 3, d_in[1], dims, st, box, es, CU_TENSOR_MAP_INTERLEAVE_NONE,
        CU_TENSOR_MAP_SWIZZLE_64B, CU_TENSOR_MAP_L2_PROMOTION_L2_128B, CU_TENSOR_MAP_FLOAT_OOB_FILL_NONE);
  }
  {
    cuuint64_t dims[3] = {64, 512, 8}, st[2] = {1024, 128};
    cuuint32_t box[3] = {64, 64, 2};
    enc(&mo, CU_TENSOR_MAP_DATA_TYPE_BFLOAT16, 3, d_in[3], dims, st, box, es, CU_TENSOR_MAP_INTERLEAVE_NONE,
        CU_TENSOR_MAP_SWIZZLE_128B, CU_TENSOR_MAP_L2_PROMOTION_L2_128B, CU_TENSOR_MAP_FLOAT_OOB_FILL_NONE);
  }
  {
    cuuint64_t dims[5] = {512, 2, 4, 4, 64}, st[4] = {1024, 8192, 2048, 32768};
    cuuint32_t box[5] = {64, 2, 4, 4, 4};
    enc(&mu, CU_TENSOR_MAP_DATA_TYPE_BFLOAT16, 5, d_in[4], dims, st, box, es, CU_TENSOR_MAP_INTERLEAVE_NONE,
        CU_TENSOR_MAP_SWIZZLE_128B, CU_TENSOR_MAP_L2_PROMOTION_L2_128B, CU_TENSOR_MAP_FLOAT_OOB_FILL_NONE);
  }
  {
    cuuint64_t dims[3] = {64, 2048, 16}, st[2] = {2048, 128};
    cuuint32_t box[3] = {64, 16, 2};
    enc(&mout, CU_TENSOR_MAP_DATA_TYPE_BFLOAT16, 3, d_out, dims, st, box, es, CU_TENSOR_MAP_INTERLEAVE_NONE,
        CU_TENSOR_MAP_SWIZZLE_128B, CU_TENSOR_MAP_L2_PROMOTION_NONE, CU_TENSOR_MAP_FLOAT_OOB_FILL_NONE);
  }
  Params P;
  P.x = (const __nv_bfloat16*)d_in[0];
  P.wphi = (const __nv_bfloat16*)d_in[2];
  P.wo = (const __nv_bfloat16*)d_in[3];
  P.logA = (const __nv_bfloat16*)d_in[5];
  P.Aim = (const __nv_bfloat16*)d_in[6];
  P.Cre = (const __nv_bfloat16*)d_in[7];
  P.Cim = (const __nv_bfloat16*)d_in[8];
  P.logdt = (const __nv_bfloat16*)d_in[9];
  P.Dskip = (const __nv_bfloat16*)d_in[10];
  P.out = (__nv_bfloat16*)d_out;
  cudaGetSymbolAddress((void**)&P.xs, g_x);
  P.ts = nullptr;
  cudaFuncSetAttribute(fused_kernel, cudaFuncAttributeMaxDynamicSharedMemorySize, SMEM_BYTES);
  fused_kernel<<<NCTA, NTHREADS, SMEM_BYTES>>>(P, mx, mw, mo, mu, mout);
}
```

```cpp
#include <cuda_runtime.h>
#include <cuda_bf16.h>
#include <cuda.h>
#include <stdint.h>

#define DBG_TS 0

namespace {

constexpr int NTHREADS = 512;
constexpr int NCTA = 128;
constexpr int OFF_W = 0;
constexpr int OFF_X = 98304;
constexpr int OFF_U = OFF_X + 65536;
constexpr int U_CH = 4416, U_ODD = 2240, U_PAD = 128;
constexpr int OFF_STG0 = OFF_U + 18432;
constexpr int OFF_T = OFF_STG0 + 24576;
constexpr int T_CH = 5216;
constexpr int T_D = 0;
constexpr int T_5 = 2144;
constexpr int T_3 = T_5 + 384;
constexpr int T_7 = T_5 + 1024;
constexpr int T_9 = T_7 + 320;
constexpr int T_KC = T_9 + 320;
constexpr int T_ST = T_5 - 1024;
constexpr int OFF_PHI = OFF_T + 4 * T_CH;
constexpr int OFF_BAR = OFF_PHI + 1024;
constexpr int SMEM_BYTES = OFF_BAR + 512;
constexpr uint32_t SB = 1024;
static_assert(T_KC + 2 * 656 <= T_CH, "table size");
static_assert(SMEM_BYTES <= 232448, "smem");
constexpr int MB_URAW = 0, MB_FULL = 1  , MB_WO = 17, MB_UFULL = 18, MB_OA = 19, MB_OB = 20, MB_OC = 21,
              MB_EMPTY = 22  , MB_CLOSE = 38;
__host__ __device__ constexpr uint32_t BAR(int i) { return SB + OFF_BAR + 8 * i; }
constexpr int NB_WG0 = 1, NB_ODONE = 2, NB_ST0 = 3  , NB_KV = 5, NB_YZ = 6, NB_INIT = 7, NB_PREP = 8, NB_PROD = 9, NB_RDY = 10, NB_BDONE = 11, NB_ZERO = 12;
#define ZERO_N 1024
#define ZERO_STEP 7
#define STEPU 0
#define STEPPF 0
constexpr int STEP_PF = STEPPF, STEP_U = STEPU;
constexpr int SPIN_MAX = 1 << 16;

constexpr int X_CNT = 0;
constexpr int X_PART = 128;
constexpr int X_O = X_PART + 16 * 8 * 144;
constexpr int X_Y = X_O + 32 * 32 * 128;
constexpr int X_UT = X_Y + 512 * 8 * 32;
constexpr int X_SIZE = X_UT + 512 * (U_CH / 16);
__device__ __align__(128) uint4 g_x[X_SIZE];
extern __shared__ uint8_t smem_raw[];
#define TS(i) do {} while (0)
#define TS1(i) do {} while (0)
#define GT(i) do {} while (0)

__device__ __forceinline__ uint32_t smem_u32(const void* p) { return (uint32_t)__cvta_generic_to_shared(p); }
__device__ __forceinline__ void mbar_arrive(uint32_t b) {
  asm volatile("mbarrier.arrive.shared::cta.b64 _, [%0];" ::"r"(b) : "memory");
}
__device__ __forceinline__ void mbar_wait(uint32_t b) {
  uint32_t done = 0;
#pragma unroll 1
  for (int i = 0; i < SPIN_MAX && !done; i++) {
    asm volatile("{\n.reg .pred p;\nmbarrier.try_wait.parity.shared::cta.b64 p, [%1], 0, 4000;\nselp.u32 %0, 1, 0, p;\n}\n"
                 : "=r"(done) : "r"(b) : "memory");
  }
}
__device__ __forceinline__ void mbar_init(uint32_t b, int n) {
  asm volatile("mbarrier.init.shared::cta.b64 [%0], %1;" ::"r"(b), "r"(n) : "memory");
}
__device__ __forceinline__ void mbar_expect(uint32_t b, int bytes) {
  asm volatile("mbarrier.arrive.expect_tx.shared::cta.b64 _, [%0], %1;" ::"r"(b), "r"(bytes) : "memory");
}
__device__ __forceinline__ void nb_sync(int id, int n) { asm volatile("bar.sync %0, %1;" ::"r"(id), "r"(n) : "memory"); }
__device__ __forceinline__ void nb_arrive(int id, int n) { asm volatile("bar.arrive %0, %1;" ::"r"(id), "r"(n) : "memory"); }
#define ELECT "{\n.reg .pred p;\nelect.sync _|p, 0xffffffff;\n@p "
__device__ __forceinline__ void e_expect(uint32_t b, int bytes) {
  asm volatile(ELECT "mbarrier.arrive.expect_tx.shared::cta.b64 _, [%0], %1;\n}\n" ::"r"(b), "r"(bytes) : "memory");
}
__device__ __forceinline__ void e_tma2d(uint32_t dst, const CUtensorMap* m, uint32_t bar, int c0, int c1) {
  asm volatile(ELECT "cp.async.bulk.tensor.2d.shared::cluster.global.mbarrier::complete_tx::bytes [%0], [%1, {%3,%4}], [%2];\n}\n"
               ::"r"(dst), "l"(m), "r"(bar), "r"(c0), "r"(c1) : "memory");
}
__device__ __forceinline__ void e_tma3d(uint32_t dst, const CUtensorMap* m, uint32_t bar, int c0, int c1, int c2) {
  asm volatile(ELECT "cp.async.bulk.tensor.3d.shared::cluster.global.mbarrier::complete_tx::bytes [%0], [%1, {%3,%4,%5}], [%2];\n}\n"
               ::"r"(dst), "l"(m), "r"(bar), "r"(c0), "r"(c1), "r"(c2) : "memory");
}
__device__ __forceinline__ void e_tma5d(uint32_t dst, const CUtensorMap* m, uint32_t bar, int c0, int c4) {
  asm volatile(ELECT "cp.async.bulk.tensor.5d.shared::cluster.global.mbarrier::complete_tx::bytes [%0], [%1, {%3,%5,%5,%5,%4}], [%2];\n}\n"
               ::"r"(dst), "l"(m), "r"(bar), "r"(c0), "r"(c4), "r"(0) : "memory");
}
__device__ __forceinline__ void e_bulk(uint32_t dst, const void* src, int bytes, uint32_t bar) {
  asm volatile(ELECT "cp.async.bulk.shared::cluster.global.mbarrier::complete_tx::bytes [%0], [%1], %2, [%3];\n}\n"
               ::"r"(dst), "l"(src), "r"(bytes), "r"(bar) : "memory");
}
__device__ __forceinline__ void e_prefetch(const void* p, int bytes) {
  asm volatile(ELECT "cp.async.bulk.prefetch.L2.global [%0], %1;\n}\n" ::"l"(p), "r"(bytes) : "memory");
}
__device__ __forceinline__ void e_store3d(const CUtensorMap* m, uint32_t src, int c1, int c2) {
  asm volatile(ELECT "cp.async.bulk.tensor.3d.global.shared::cta.bulk_group [%0, {%4,%2,%3}], [%1];\n"
               "@p cp.async.bulk.commit_group;\n@p cp.async.bulk.wait_group.read 0;\n}\n"
               ::"l"(m), "r"(src), "r"(c1), "r"(c2), "r"(0) : "memory");
}
__host__ __device__ constexpr uint64_t mkdesc(uint32_t addr, uint32_t lbo, uint32_t sbo, int swz) {
  return (uint64_t)((addr & 0x3FFFF) >> 4) | ((uint64_t)(lbo >> 4) << 16) | ((uint64_t)(sbo >> 4) << 32) |
         ((uint64_t)swz << 62);
}
#define WG_FENCE() asm volatile("wgmma.fence.sync.aligned;" ::: "memory")
#define WG_COMMIT() asm volatile("wgmma.commit_group.sync.aligned;" ::: "memory")
#define WG_WAIT(n) asm volatile("wgmma.wait_group.sync.aligned " #n ";" ::: "memory")

__device__ __forceinline__ void mma(float& d0, float& d1, float& d2, float& d3, uint32_t a0, uint32_t a1, uint32_t a2,
                                    uint32_t a3, uint32_t b0, uint32_t b1) {
  asm volatile("mma.sync.aligned.m16n8k16.row.col.f32.bf16.bf16.f32 {%0,%1,%2,%3},{%4,%5,%6,%7},{%8,%9},{%0,%1,%2,%3};"
               : "+f"(d0), "+f"(d1), "+f"(d2), "+f"(d3)
               : "r"(a0), "r"(a1), "r"(a2), "r"(a3), "r"(b0), "r"(b1));
}
__device__ __forceinline__ void mmac(float (&d)[4], uint32_t a0, uint32_t a1, uint32_t a2, uint32_t a3, uint32_t b0,
                                     uint32_t b1, const float (&c)[4]) {
  asm volatile("mma.sync.aligned.m16n8k16.row.col.f32.bf16.bf16.f32 {%0,%1,%2,%3},{%4,%5,%6,%7},{%8,%9},{%10,%11,%12,%13};"
               : "=f"(d[0]), "=f"(d[1]), "=f"(d[2]), "=f"(d[3])
               : "r"(a0), "r"(a1), "r"(a2), "r"(a3), "r"(b0), "r"(b1), "f"(c[0]), "f"(c[1]), "f"(c[2]), "f"(c[3]));
}
__device__ __forceinline__ void mma_p(int p, float (&d)[4], uint32_t a0, uint32_t a1, uint32_t a2, uint32_t a3, uint32_t b0, uint32_t b1) {
  asm volatile("{\n.reg .pred q;\nsetp.ne.b32 q, %10, 0;\n"
               "@q mma.sync.aligned.m16n8k16.row.col.f32.bf16.bf16.f32 {%0,%1,%2,%3},{%4,%5,%6,%7},{%8,%9},{%0,%1,%2,%3};\n}\n"
               : "+f"(d[0]), "+f"(d[1]), "+f"(d[2]), "+f"(d[3])
               : "r"(a0), "r"(a1), "r"(a2), "r"(a3), "r"(b0), "r"(b1), "r"(p));
}
__device__ __forceinline__ void mmac_p(int p, float (&d)[4], uint32_t a0, uint32_t a1, uint32_t a2, uint32_t a3, uint32_t b0,
                                       uint32_t b1, const float (&c)[4]) {
  asm volatile("{\n.reg .pred q;\nsetp.ne.b32 q, %14, 0;\n"
               "@q mma.sync.aligned.m16n8k16.row.col.f32.bf16.bf16.f32 {%0,%1,%2,%3},{%4,%5,%6,%7},{%8,%9},{%10,%11,%12,%13};\n}\n"
               : "+f"(d[0]), "+f"(d[1]), "+f"(d[2]), "+f"(d[3])
               : "r"(a0), "r"(a1), "r"(a2), "r"(a3), "r"(b0), "r"(b1), "f"(c[0]), "f"(c[1]), "f"(c[2]), "f"(c[3]), "r"(p));
}
__device__ __forceinline__ void mma_k8(float (&d)[4], uint32_t a0, uint32_t a1, uint32_t b0) {
  asm volatile("mma.sync.aligned.m16n8k8.row.col.f32.bf16.bf16.f32 {%0,%1,%2,%3},{%4,%5},{%6},{%0,%1,%2,%3};"
               : "+f"(d[0]), "+f"(d[1]), "+f"(d[2]), "+f"(d[3]) : "r"(a0), "r"(a1), "r"(b0));
}
__device__ __forceinline__ void mma0(float& d0, float& d1, float& d2, float& d3, uint32_t a0, uint32_t a1, uint32_t a2,
                                     uint32_t a3, uint32_t b0, uint32_t b1) {
  asm volatile("mma.sync.aligned.m16n8k16.row.col.f32.bf16.bf16.f32 {%0,%1,%2,%3},{%4,%5,%6,%7},{%8,%9},{%10,%10,%10,%10};"
               : "=f"(d0), "=f"(d1), "=f"(d2), "=f"(d3)
               : "r"(a0), "r"(a1), "r"(a2), "r"(a3), "r"(b0), "r"(b1), "f"(0.f));
}
__device__ __forceinline__ uint32_t pack_bf(float lo, float hi) {
  uint32_t r;
  asm("cvt.rn.bf16x2.f32 %0, %1, %2;" : "=r"(r) : "f"(hi), "f"(lo));
  return r;
}
__device__ __forceinline__ float bf_lo(uint32_t w) { return __uint_as_float(w << 16); }
__device__ __forceinline__ float bf_hi(uint32_t w) { return __uint_as_float(w & 0xffff0000u); }
__device__ __forceinline__ float bf_round(float x) { return __bfloat162float(__float2bfloat16_rn(x)); }
__device__ __forceinline__ uint32_t bmax2(uint32_t a, uint32_t b) {
  uint32_t r; asm("max.bf16x2 %0, %1, %2;" : "=r"(r) : "r"(a), "r"(b)); return r;
}
__device__ __forceinline__ uint32_t bmin2(uint32_t a, uint32_t b) {
  uint32_t r; asm("min.bf16x2 %0, %1, %2;" : "=r"(r) : "r"(a), "r"(b)); return r;
}
__device__ __forceinline__ float ex2(float x) { float r; asm("ex2.approx.ftz.f32 %0, %1;" : "=f"(r) : "f"(x)); return r; }
__device__ __forceinline__ float rcp(float x) { float r; asm("rcp.approx.ftz.f32 %0, %1;" : "=f"(r) : "f"(x)); return r; }
__device__ __forceinline__ void ldsm4(uint32_t (&r)[4], uint32_t a) {
  asm volatile("ldmatrix.sync.aligned.m8n8.x4.shared.b16 {%0,%1,%2,%3}, [%4];"
               : "=r"(r[0]), "=r"(r[1]), "=r"(r[2]), "=r"(r[3]) : "r"(a) : "memory");
}
__device__ __forceinline__ void ldsm4t(uint32_t (&r)[4], uint32_t a) {
  asm volatile("ldmatrix.sync.aligned.m8n8.x4.trans.shared.b16 {%0,%1,%2,%3}, [%4];"
               : "=r"(r[0]), "=r"(r[1]), "=r"(r[2]), "=r"(r[3]) : "r"(a) : "memory");
}
__device__ __forceinline__ void stsm4(uint32_t a, uint32_t r0, uint32_t r1, uint32_t r2, uint32_t r3) {
  asm volatile("stmatrix.sync.aligned.m8n8.x4.shared.b16 [%0], {%1,%2,%3,%4};"
               ::"r"(a), "r"(r0), "r"(r1), "r"(r2), "r"(r3) : "memory");
}
__device__ __forceinline__ uint32_t lds32(uint32_t a) {
  uint32_t r; asm volatile("ld.shared.u32 %0, [%1];" : "=r"(r) : "r"(a) : "memory"); return r;
}
__device__ __forceinline__ uint32_t lds16(uint32_t a) {
  uint32_t r; asm volatile("{\n.reg .u16 h;\nld.shared.u16 h, [%1];\ncvt.u32.u16 %0, h;\n}\n" : "=r"(r) : "r"(a) : "memory"); return r;
}
__device__ __forceinline__ uint2 lds64(uint32_t a) {
  uint2 r; asm volatile("ld.shared.v2.u32 {%0,%1}, [%2];" : "=r"(r.x), "=r"(r.y) : "r"(a) : "memory"); return r;
}
__device__ __forceinline__ uint4 lds128(uint32_t a) {
  uint4 r;
  asm volatile("ld.shared.v4.u32 {%0,%1,%2,%3}, [%4];" : "=r"(r.x), "=r"(r.y), "=r"(r.z), "=r"(r.w) : "r"(a) : "memory");
  return r;
}
__device__ __forceinline__ void sts32(uint32_t a, uint32_t v) { asm volatile("st.shared.u32 [%0], %1;" ::"r"(a), "r"(v) : "memory"); }
__device__ __forceinline__ void sts16(uint32_t a, uint32_t v) {
  asm volatile("{\n.reg .u16 h;\ncvt.u16.u32 h, %1;\nst.shared.u16 [%0], h;\n}\n" ::"r"(a), "r"(v) : "memory");
}
__device__ __forceinline__ void sts64(uint32_t a, uint32_t x, uint32_t y) {
  asm volatile("st.shared.v2.u32 [%0], {%1,%2};" ::"r"(a), "r"(x), "r"(y) : "memory");
}
__device__ __forceinline__ void sts128(uint32_t a, uint32_t x, uint32_t y, uint32_t z, uint32_t w) {
  asm volatile("st.shared.v4.u32 [%0], {%1,%2,%3,%4};" ::"r"(a), "r"(x), "r"(y), "r"(z), "r"(w) : "memory");
}
__device__ __forceinline__ uint4 ld_x(const uint4* p) {
  uint4 r;
  asm volatile("{\n.reg .b128 t;\nld.relaxed.gpu.global.b128 t, [%4];\nmov.b128 {%0,%1,%2,%3}, t;\n}\n"
               : "=r"(r.x), "=r"(r.y), "=r"(r.z), "=r"(r.w) : "l"(p) : "memory");
  return r;
}
__device__ __forceinline__ uint32_t ld_x32(const uint32_t* p) {
  uint32_t r; asm volatile("ld.relaxed.gpu.global.u32 %0, [%1];" : "=r"(r) : "l"(p) : "memory"); return r;
}
__device__ __forceinline__ void st_x(uint4* p, uint32_t x, uint32_t y, uint32_t z, uint32_t w) {
  asm volatile("{\n.reg .b128 t;\nmov.b128 t, {%1,%2,%3,%4};\nst.relaxed.gpu.global.b128 [%0], t;\n}\n"
               ::"l"(p), "r"(x), "r"(y), "r"(z), "r"(w) : "memory");
}
__device__ __forceinline__ void st_x_p(int p, uint4* a, uint32_t x, uint32_t y, uint32_t z, uint32_t w) {
  asm volatile("{\n.reg .b128 t;\n.reg .pred q;\nsetp.ne.b32 q, %5, 0;\nmov.b128 t, {%1,%2,%3,%4};\n@q st.relaxed.gpu.global.b128 [%0], t;\n}\n"
               ::"l"(a), "r"(x), "r"(y), "r"(z), "r"(w), "r"(p) : "memory");
}
__device__ __forceinline__ void sts64_p(int p, uint32_t a, uint32_t x, uint32_t y) {
  asm volatile("{\n.reg .pred q;\nsetp.ne.b32 q, %3, 0;\n@q st.shared.v2.u32 [%0], {%1,%2};\n}\n" ::"r"(a), "r"(x), "r"(y), "r"(p) : "memory");
}
__device__ __forceinline__ void st_x32(uint32_t* p, uint32_t x) {
  asm volatile("st.relaxed.gpu.global.u32 [%0], %1;" ::"l"(p), "r"(x) : "memory");
}
__device__ __forceinline__ uint32_t nz(uint32_t w) { return max(w, 1u); }
__device__ __forceinline__ uint32_t fu(float x) { return __float_as_uint(x); }
__device__ __forceinline__ float uf(uint32_t x) { return __uint_as_float(x); }

__device__ __forceinline__ void wgmma_ss_n96(float (&d)[48], uint64_t da, uint64_t db, int sc) {
  asm volatile("{\n.reg .pred p;\nsetp.ne.b32 p, %50, 0;\n"
      "wgmma.mma_async.sync.aligned.m64n96k16.f32.bf16.bf16 "
      "{%0,%1,%2,%3,%4,%5,%6,%7,%8,%9,%10,%11,%12,%13,%14,%15,%16,%17,%18,%19,%20,%21,%22,%23,%24,%25,%26,%27,%28,%29,%30,%31,%32,%33,%34,%35,%36,%37,%38,%39,%40,%41,%42,%43,%44,%45,%46,%47}, "
      "%48, %49, p, 1, 1, 0, 1;\n}\n"
      : "+f"(d[0]), "+f"(d[1]), "+f"(d[2]), "+f"(d[3]), "+f"(d[4]), "+f"(d[5]), "+f"(d[6]), "+f"(d[7]),
        "+f"(d[8]), "+f"(d[9]), "+f"(d[10]), "+f"(d[11]), "+f"(d[12]), "+f"(d[13]), "+f"(d[14]), "+f"(d[15]),
        "+f"(d[16]), "+f"(d[17]), "+f"(d[18]), "+f"(d[19]), "+f"(d[20]), "+f"(d[21]), "+f"(d[22]), "+f"(d[23]),
        "+f"(d[24]), "+f"(d[25]), "+f"(d[26]), "+f"(d[27]), "+f"(d[28]), "+f"(d[29]), "+f"(d[30]), "+f"(d[31]),
        "+f"(d[32]), "+f"(d[33]), "+f"(d[34]), "+f"(d[35]), "+f"(d[36]), "+f"(d[37]), "+f"(d[38]), "+f"(d[39]),
        "+f"(d[40]), "+f"(d[41]), "+f"(d[42]), "+f"(d[43]), "+f"(d[44]), "+f"(d[45]), "+f"(d[46]), "+f"(d[47])
      : "l"(da), "l"(db), "r"(sc));
}

__device__ __forceinline__ void wgmma_ss_n128(float (&d)[64], uint64_t da, uint64_t db, int sc) {
  asm volatile("{\n.reg .pred p;\nsetp.ne.b32 p, %66, 0;\n"
      "wgmma.mma_async.sync.aligned.m64n128k16.f32.bf16.bf16 "
      "{%0,%1,%2,%3,%4,%5,%6,%7,%8,%9,%10,%11,%12,%13,%14,%15,%16,%17,%18,%19,%20,%21,%22,%23,%24,%25,%26,%27,%28,%29,%30,%31,%32,%33,%34,%35,%36,%37,%38,%39,%40,%41,%42,%43,%44,%45,%46,%47,%48,%49,%50,%51,%52,%53,%54,%55,%56,%57,%58,%59,%60,%61,%62,%63}, "
      "%64, %65, p, 1, 1, 0, 1;\n}\n"
      : "+f"(d[0]), "+f"(d[1]), "+f"(d[2]), "+f"(d[3]), "+f"(d[4]), "+f"(d[5]), "+f"(d[6]), "+f"(d[7]),
        "+f"(d[8]), "+f"(d[9]), "+f"(d[10]), "+f"(d[11]), "+f"(d[12]), "+f"(d[13]), "+f"(d[14]), "+f"(d[15]),
        "+f"(d[16]), "+f"(d[17]), "+f"(d[18]), "+f"(d[19]), "+f"(d[20]), "+f"(d[21]), "+f"(d[22]), "+f"(d[23]),
        "+f"(d[24]), "+f"(d[25]), "+f"(d[26]), "+f"(d[27]), "+f"(d[28]), "+f"(d[29]), "+f"(d[30]), "+f"(d[31]),
        "+f"(d[32]), "+f"(d[33]), "+f"(d[34]), "+f"(d[35]), "+f"(d[36]), "+f"(d[37]), "+f"(d[38]), "+f"(d[39]),
        "+f"(d[40]), "+f"(d[41]), "+f"(d[42]), "+f"(d[43]), "+f"(d[44]), "+f"(d[45]), "+f"(d[46]), "+f"(d[47]),
        "+f"(d[48]), "+f"(d[49]), "+f"(d[50]), "+f"(d[51]), "+f"(d[52]), "+f"(d[53]), "+f"(d[54]), "+f"(d[55]),
        "+f"(d[56]), "+f"(d[57]), "+f"(d[58]), "+f"(d[59]), "+f"(d[60]), "+f"(d[61]), "+f"(d[62]), "+f"(d[63])
      : "l"(da), "l"(db), "r"(sc));
}

struct Params {
  const __nv_bfloat16 *logA, *Aim, *Cre, *Cim, *logdt, *Dskip, *x, *wphi, *wo;
  __nv_bfloat16* out;
  uint4* xs;
  long long* ts;
};

__device__ __forceinline__ uint4 tr_row(const uint4 (&v)[8], int i) {
  uint32_t o[4];
#pragma unroll
  for (int m = 0; m < 4; m++) {
    const uint4 &ra = v[2 * m], &rb = v[2 * m + 1];
    const int k = i >> 1;
    const uint32_t xa = k == 0 ? ra.x : k == 1 ? ra.y : k == 2 ? ra.z : ra.w;
    const uint32_t xb = k == 0 ? rb.x : k == 1 ? rb.y : k == 2 ? rb.z : rb.w;
    o[m] = __byte_perm(xa, xb, (i & 1) ? 0x7632 : 0x5410);
  }
  return make_uint4(o[0], o[1], o[2], o[3]);
}

struct cpx { float r, i; };
__device__ __forceinline__ cpx cmul(cpx a, cpx b) { return {a.r * b.r - a.i * b.i, a.r * b.i + a.i * b.r}; }
__device__ __forceinline__ cpx csq(cpx a) { return {a.r * a.r - a.i * a.i, 2.f * (a.r * a.i)}; }
__device__ __forceinline__ cpx polar(float e, float t) {
  const float m = ex2(e);
  return {m * __cosf(t), m * __sinf(t)};
}

struct KgenRaw { unsigned short la, ai, cr, ci, ldt; };
__device__ __forceinline__ KgenRaw kgen_load(const Params& P, int d, int unit, int lane) {
  const int o = d * 128 + unit * 32 + lane;
  return {__ldg((const unsigned short*)P.logA + o), __ldg((const unsigned short*)P.Aim + o), __ldg((const unsigned short*)P.Cre + o),
          __ldg((const unsigned short*)P.Cim + o), __ldg((const unsigned short*)P.logdt + d)};
}
__device__ __forceinline__ void kgen_unit(const KgenRaw& r, int lane, uint32_t buf, uint32_t open_bar, float& dt,
                                          float (&k)[5][4], float& k2048) {
  dt = bf_round(expf(bf_lo(r.ldt)));
  const float a2 = -(bf_round(expf(bf_lo(r.la))) * dt) * 1.4426950408889634f;
  const float f = bf_lo(r.ai) * dt;
  const float r128 = f * 20.371832715762604f;
  const cpx C = {bf_lo(r.cr), -bf_lo(r.ci)};
  const uint32_t sa = buf + (lane & 7) * 128 + ((((lane >> 3) ^ lane) & 7) << 4);
  const uint32_t lb = buf + (lane >> 3) * 128 + (((lane ^ (lane >> 3)) & 7) << 4);
  const uint32_t la = buf + ((lane >> 3) & 1) * 1024 + (lane >> 4) * 128 + (((lane ^ (lane >> 4)) & 7) << 4);
  auto put = [&](const cpx (&v)[8], uint32_t off) {
    stsm4(sa + off, pack_bf(v[0].r, v[0].i), pack_bf(v[1].r, v[1].i), pack_bf(v[2].r, v[2].i), pack_bf(v[3].r, v[3].i));
    stsm4((sa ^ 64) + off, pack_bf(v[4].r, v[4].i), pack_bf(v[5].r, v[5].i), pack_bf(v[6].r, v[6].i), pack_bf(v[7].r, v[7].i));
  };
  uint32_t A[4][4], B[5][2][4];
  auto getB = [&](int j, uint32_t off) {
    __syncwarp();
    ldsm4(B[j][0], lb + off);
    ldsm4(B[j][1], (lb ^ 64) + 512 + off);
  };
  cpx t0[8], t1[8], t2[8], t3[8], t4[8];
  t0[0] = {1.f, 0.f};
  t0[1] = polar(a2, f);
  t1[0] = polar(a2 * 128.f, (r128 - rintf(r128)) * 6.283185307179586f);
  t0[2] = csq(t0[1]); t0[4] = csq(t0[2]);
  t2[0] = csq(t1[0]); t3[0] = csq(t2[0]); t4[0] = csq(t3[0]);
  t0[3] = cmul(t0[2], t0[1]); t0[5] = cmul(t0[4], t0[1]); t0[6] = cmul(t0[4], t0[2]); t0[7] = cmul(t0[4], t0[3]);
  put(t0, 0); getB(0, 0);
  {
    cpx w8 = csq(t0[4]);
    w8.i = -w8.i;
    const cpx w16 = csq(w8), w32 = csq(w16), w64 = csq(w32);
    cpx a[8];
    a[0] = C; a[1] = cmul(C, w8);
    a[2] = cmul(a[0], w16); a[3] = cmul(a[1], w16);
#pragma unroll
    for (int i = 0; i < 4; i++) a[4 + i] = cmul(a[i], w32);
    put(a, 0);
#pragma unroll
    for (int i = 0; i < 8; i++) a[i] = cmul(a[i], w64);
    put(a, 1024);
    __syncwarp();
#pragma unroll
    for (int s = 0; s < 4; s++) ldsm4(A[s], (la ^ (s << 5)) + s * 256);
  }
#pragma unroll
  for (int i = 1; i < 8; i++) t1[i] = cmul(t0[i], t1[0]);
  put(t1, 0); getB(1, 0);
#pragma unroll
  for (int i = 1; i < 8; i++) t2[i] = cmul((i & 1) ? t1[i & 6] : t0[i & 6], t2[0]);
  put(t2, 1024); getB(2, 1024);
#pragma unroll
  for (int i = 1; i < 8; i++) t3[i] = cmul((i & 2) ? t2[i & 5] : ((i & 1) ? t1[i & 4] : t0[i & 4]), t3[0]);
  put(t3, 0); getB(3, 0);
#pragma unroll
  for (int i = 1; i < 8; i++) t4[i] = cmul((i & 4) ? t3[i & 3] : ((i & 2) ? t2[i & 1] : t1[0]), t4[0]);
  put(t4, 1024); getB(4, 1024);
  const cpx we = csq(t4[0]);
  k2048 += C.r * we.r + C.i * we.i;
  if (open_bar) mbar_wait(open_bar);
#pragma unroll
  for (int s = 0; s < 4; s++)
#pragma unroll
    for (int j = 0; j < 5; j++)
      mma(k[j][0], k[j][1], k[j][2], k[j][3], A[s][0], A[s][1], A[s][2], A[s][3], B[j][s >> 1][2 * (s & 1)], B[j][s >> 1][2 * (s & 1) + 1]);
}

__device__ __forceinline__ void build_tables(uint32_t tb, int lane, float (&k)[5][4], float k2048) {
  const int g = lane >> 2, c = lane & 3;
  const uint32_t kc = tb + T_KC + 16;
  {
    const uint32_t a0 = kc + 16 * g + 4 * c, a2 = kc + 2 * (256 + 4 * g + c);
    const uint32_t a3 = kc + 2 * (384 + 2 * g + 64 * (c & 1) + (c >> 1)), a4 = kc + 2 * (512 + g + 32 * c);
#pragma unroll
    for (int r = 0; r < 2; r++) {
      sts32(a0 + 128 * r, pack_bf(k[0][2 * r], k[0][2 * r + 1]));
      sts32(a0 + 128 * r + 256, pack_bf(k[1][2 * r], k[1][2 * r + 1]));
      const uint32_t w2 = pack_bf(k[2][2 * r], k[2][2 * r + 1]);
      const uint32_t w3 = pack_bf(k[3][2 * r], k[3][2 * r + 1]);
      const uint32_t w4 = pack_bf(k[4][2 * r], k[4][2 * r + 1]);
      sts16(a2 + 64 * r, w2); sts16(a2 + 64 * r + 128, w2 >> 16);
      sts16(a3 + 32 * r, w3); sts16(a3 + 32 * r + 64, w3 >> 16);
      sts16(a4 + 16 * r, w4); sts16(a4 + 16 * r + 32, w4 >> 16);
    }
  }
  if (lane == 0) { sts16(kc + 2 * 640, pack_bf(k2048, 0.f)); sts16(kc - 2, 0); }
  __syncwarp();
  const uint32_t td = tb + T_D + 32;
  {
    const uint4 v = lds128(kc + 16 * lane);
    const uint32_t pv = lds16(kc + 16 * lane - 2);
    sts128(td + 32 * lane, __byte_perm(v.x, pv, 0x5410), __byte_perm(v.x, v.x, 0x1032), __byte_perm(v.y, v.x, 0x7610),
           __byte_perm(v.y, v.y, 0x1032));
    sts128(td + 32 * lane + 16, __byte_perm(v.z, v.y, 0x7610), __byte_perm(v.z, v.z, 0x1032),
           __byte_perm(v.w, v.z, 0x7610), __byte_perm(v.w, v.w, 0x1032));
  }
  {
    const uint2 v = lds64(kc + 512 + 8 * lane);
    const uint32_t k4 = lds16(kc + 512 + 8 * lane + 8);
    const uint32_t pv = lds16(kc + (lane == 0 ? 510 : 512 + 8 * lane));
    const uint32_t k22 = __byte_perm(v.y, v.y, 0x1010);
    sts128(td + 1024 + 32 * lane, __byte_perm(v.x, pv, 0x5410), __byte_perm(v.x, v.x, 0x1010),
           __byte_perm(v.x, v.x, 0x1032), __byte_perm(v.y, v.x, 0x7610));
    sts128(td + 1024 + 32 * lane + 16, k22, k22, __byte_perm(v.y, v.y, 0x1032), __byte_perm(k4, v.y, 0x7610));
  }
  {
    const uint32_t kk = lds16(kc + 2 * 384);
    const uint32_t w = lane < 3 ? (kk | (kk << 16)) : (lane == 3 ? (kk << 16) : 0u);
    if (lane < 24) sts32(td + 4 * (lane < 16 ? 512 + lane : lane - 24), w);
    const uint32_t lo_ = lds16(kc + 2 * 511), le_ = lds16(kc + 2 * 512);
    const uint32_t ja = tb + T_5 + (lane < 16 ? 4 * lane : 256 + 4 * lane);
    sts32(ja, lane == 16 ? (le_ << 16) : 0u);
    sts32(ja + 384, lane == 16 ? (lo_ << 16) : 0u);
    sts32(tb + (lane < 16 ? T_7 : T_9 - 64) + 4 * lane, 0u);
  }
#pragma unroll
  for (int s = 0; s < 2; s++) {
    const uint32_t b = kc + 2 * (s ? 512 : 384) + 8 * lane;
    const uint2 v = lds64(b);
    uint32_t em = lds16(b - 2), e0 = v.x;
    const uint32_t e4 = lds16(b + 8);
    if (lane == 0) { em = 0; e0 = 0; }
    sts64(tb + (s ? T_7 : T_3) + 64 + 8 * lane, __byte_perm(v.x, em, 0x5432), __byte_perm(v.y, v.x, 0x7632));
    sts64(tb + (s ? T_9 : T_5) + 64 + 8 * lane, __byte_perm(v.y, e0, 0x5410), __byte_perm(e4, v.y, 0x5410));
  }
  __syncwarp();
}

__device__ __forceinline__ uint32_t box2w(int lo, int n, int o) {
  return ((unsigned)(o - lo) < (unsigned)n ? 0x3F80u : 0u) | ((unsigned)(o + 1 - lo) < (unsigned)n ? 0x3F800000u : 0u);
}

__device__ __forceinline__ void conv_channel(uint32_t ub, uint32_t tb, int lane, uint4* ydst) {
  const int g = lane >> 2, c = lane & 3, x = g - 2 * c;
  const uint32_t st = tb + T_ST + lane * 8;
  const int mi = lane >> 3;
  const uint32_t qa = ub + U_PAD + 16 * (lane & 7) + ((mi == 0 || mi == 3) ? U_ODD : 0) - (mi == 0 ? 16 : 0);
  const uint32_t kv = lds16(tb + T_KC + 16 + 2 * 512);
  {
    const uint32_t hb = ub + U_PAD + (mi & 1) * U_ODD + 16 * ((lane >> 4) + (lane & 7)) - 16;
    const int oh = c < 2 ? 8 + 2 * c : 2 * c - 8;
    const uint32_t bx0 = box2w(g - 4, 9, 2 * c), bx1 = box2w(g - 3, 7, 2 * c), bx2 = box2w(g - 4, 9, oh), bx3 = box2w(g - 3, 7, oh);
    uint32_t f7[9], f9a[9], f9b[9];
    const uint32_t fa = tb + T_7 + 4 * (8 + x);
#pragma unroll
    for (int m = 0; m < 9; m++) {
      f7[m] = lds32(fa + 32 * m);
      f9b[m] = lds32(fa + 320 + 32 * m);
      f9a[m] = lds32(fa + 316 + 32 * m);
    }
    mbar_wait(BAR(MB_EMPTY + 15));
    TS(36);
    uint32_t z09[8], z07[8], zm9[8], zm7[8];
#pragma unroll
    for (int i = 0; i < 8; i++) {
      uint32_t h[4];
      ldsm4(h, hb + 128 * i);
      float y0, y1, y2, y3, w0, w1, w2, w3;
      mma0(y0, y1, y2, y3, bx0, bx1, bx2, bx3, h[2], c < 2 ? h[3] : h[1]);
      mma0(w0, w1, w2, w3, bx0, bx1, bx2, bx3, h[1], c < 2 ? h[2] : h[0]);
      z09[i] = pack_bf(y0, y1); z07[i] = pack_bf(y2, y3);
      zm9[i] = pack_bf(w0, w1); zm7[i] = pack_bf(w2, w3);
    }
    float a[4][2][4];
#pragma unroll
    for (int kap = 0; kap < 4; kap++)
#pragma unroll
      for (int sg = 0; sg < 2; sg++)
#pragma unroll
        for (int bk = 3; bk >= kap; bk--) {
          const int m = 2 * (bk - kap) + 1;
          float(&a0)[4] = a[bk][0];
          float(&a1)[4] = a[bk][1];
          if (sg == 0 && kap == 0) {
            mma0(a0[0], a0[1], a0[2], a0[3], f9a[m], f9a[m + 1], f9a[m - 1], f9a[m], z09[0], z09[1]);
            mma0(a1[0], a1[1], a1[2], a1[3], f9b[m], f9b[m + 1], f9b[m - 1], f9b[m], zm9[0], zm9[1]);
          } else if (sg == 0) {
            mma(a0[0], a0[1], a0[2], a0[3], f9a[m], f9a[m + 1], f9a[m - 1], f9a[m], z09[2 * kap], z09[2 * kap + 1]);
            mma(a1[0], a1[1], a1[2], a1[3], f9b[m], f9b[m + 1], f9b[m - 1], f9b[m], zm9[2 * kap], zm9[2 * kap + 1]);
          } else {
            mma(a0[0], a0[1], a0[2], a0[3], f7[m], f7[m + 1], f7[m - 1], f7[m], zm7[2 * kap], zm7[2 * kap + 1]);
            mma(a1[0], a1[1], a1[2], a1[3], f7[m], f7[m + 1], f7[m - 1], f7[m], z07[2 * kap], z07[2 * kap + 1]);
          }
        }
#pragma unroll
    for (int bk = 0; bk < 4; bk++) {
      sts64(st + 256 * (8 + 2 * bk), pack_bf(a[bk][0][0], a[bk][0][1]), pack_bf(a[bk][1][0], a[bk][1][1]));
      sts64(st + 256 * (9 + 2 * bk), pack_bf(a[bk][0][2], a[bk][0][3]), pack_bf(a[bk][1][2], a[bk][1][3]));
    }
  }
  TS(44);
  {
    const int oh = c < 3 ? 2 * c : -10;
    const uint32_t bx0 = box2w(g - 10, 5, 2 * c - 8), bx1 = box2w(g - 5, 3, 2 * c - 8), bx2 = box2w(g - 10, 5, oh), bx3 = box2w(g - 5, 3, oh);
    const uint32_t lb0 = ((unsigned)(x + 5) < 2u ? kv : 0u) | ((unsigned)(x + 4) < 2u ? kv << 16 : 0u);
    const uint32_t lb1 = ((unsigned)(x - 3) < 2u ? kv : 0u) | ((unsigned)(x - 4) < 2u ? kv << 16 : 0u);
    const int q0 = g - 1, q1 = c < 3 ? g : g - 2;
    uint32_t y0a = ub + U_PAD + (q0 & 1) * U_ODD + 16 * (q0 >> 1) + 4 * c;
    uint32_t y1a = ub + U_PAD + (q1 & 1) * U_ODD + 16 * (q1 >> 1) + 4 * c;
    uint2 a5[10], a3[10];
    const uint32_t aa = tb + T_5 + 4 * (8 + 2 * g - 2 * c);
#pragma unroll
    for (int m = 0; m < 10; m++) { a5[m] = lds64(aa + 32 * m); a3[m] = lds64(aa + 384 + 32 * m); }
    float T[6][4];
#pragma unroll
    for (int i = 0; i < 6; i++) T[i][0] = T[i][1] = T[i][2] = T[i][3] = 0.f;
    uint32_t x5[2] = {0, 0}, x3[2] = {0, 0}, yb[4], lq[4];
    uint32_t lqa = qa, sta = st + 256 * 8;
    uint2 sv;
    auto fetch = [&]() {
      yb[0] = lds32(y0a); yb[1] = lds32(y1a); yb[2] = lds32(y0a + 64); yb[3] = lds32(y1a + 64);
      ldsm4(lq, lqa);
      sv = lds64(min(sta, st + 256 * 15));
      y0a += 128; y1a += 128; lqa += 128; sta += 256;
    };
    fetch();
#pragma unroll 2
    for (int kap = -1; kap < 13; kap++) {
      float yn[2][4];
      mma0(yn[0][0], yn[0][1], yn[0][2], yn[0][3], bx0, bx1, bx2, bx3, yb[0], yb[1]);
      mma0(yn[1][0], yn[1][1], yn[1][2], yn[1][3], bx0, bx1, bx2, bx3, yb[2], yb[3]);
      sts64_p(kap > 0, sta - 256 * 7, pack_bf(T[0][0], T[0][1]), pack_bf(T[0][2], T[0][3]));
#pragma unroll
      for (int i = 0; i < 5; i++)
        mmac_p((unsigned)kap < 12u - i, T[i], a5[2 * i + 1].x, a5[2 * i + 1].y, a5[2 * i].x, a5[2 * i].y, x5[0], x5[1], T[i + 1]);
      const float ci[4] = {bf_lo(sv.x), bf_hi(sv.x), bf_lo(sv.y), bf_hi(sv.y)};
      mmac_p(kap < 7, T[5], lq[0], lq[1], lq[2], lq[3], lb0, lb1, ci);
      fetch();
#pragma unroll
      for (int i = 0; i < 5; i++)
        mma_p((unsigned)kap < 12u - i, T[i], a3[2 * i + 1].x, a3[2 * i + 1].y, a3[2 * i].x, a3[2 * i].y, x3[0], x3[1]);
#pragma unroll
      for (int hh = 0; hh < 2; hh++) { x5[hh] = pack_bf(yn[hh][0], yn[hh][1]); x3[hh] = pack_bf(yn[hh][2], yn[hh][3]); }
    }
  }
  TS(45);
  {
    uint32_t F[66];
    const uint32_t fa = tb + T_D + 32 + 4 * x;
#pragma unroll
    for (int m = 0; m < 66; m++) F[m] = lds32(fa + 32 * m);
    float T[5][4];
#pragma unroll
    for (int i = 0; i < 5; i++) T[i][0] = T[i][1] = T[i][2] = T[i][3] = 0.f;
    uint32_t qd[8][4], held[2] = {0, 0};
    uint32_t qp = qa + 128 * 15, sta = st + 256 * 14;
    uint4* yd = ydst + 19 * 16;
#pragma unroll
    for (int i = 0; i < 6; i++) ldsm4(qd[i], qp - 16 * i);
    uint2 sv = lds64(sta + 256);
    float ci[4] = {bf_lo(sv.x), bf_hi(sv.x), bf_lo(sv.y), bf_hi(sv.y)};
    TS(46);
#pragma unroll 2
    for (int be = 15; be >= 0; be--) {
#pragma unroll
      for (int k = 4; k >= 1; k--)
        mmac_p(be <= 15 - k, T[k], qd[0][0], qd[0][1], qd[0][2], qd[0][3], F[16 * k + 1], F[16 * k], T[k - 1]);
      mmac(T[0], qd[0][0], qd[0][1], qd[0][2], qd[0][3], F[1], F[0], ci);
      ldsm4(qd[6], qp - 16 * 6);
      ldsm4(qd[7], qp - 16 * 7);
      sv = lds64(sta);
#pragma unroll
      for (int i = 1; i < 8; i++) {
#pragma unroll
        for (int k = 3; k >= 0; k--)
          mma_p(k == 0 || be <= 15 - k, T[k], qd[i][0], qd[i][1], qd[i][2], qd[i][3], F[16 * k + 2 * i + 1], F[16 * k + 2 * i]);
        if (i < 7) ldsm4(qd[i - 1], qp - 128 - 16 * (i - 1));
        if (i == 2) {
          const uint32_t w0 = pack_bf(T[4][0], T[4][1]), w1 = pack_bf(T[4][2], T[4][3]);
          st_x_p(be <= 10 && !(be & 1), yd, nz(w0), w1, held[0], held[1]);
          held[0] = w0; held[1] = w1;
        }
        if (i == 4) {
          if (be <= 4) sv = make_uint2(0, 0);
          ci[0] = bf_lo(sv.x); ci[1] = bf_hi(sv.x); ci[2] = bf_lo(sv.y); ci[3] = bf_hi(sv.y);
        }
      }
      qp -= 128; sta -= 256; yd -= 16;
    }
#pragma unroll
    for (int B = 1; B >= 0; B--)
      st_x(ydst + B * 32, nz(pack_bf(T[2 * B][0], T[2 * B][1])), pack_bf(T[2 * B][2], T[2 * B][3]),
           pack_bf(T[2 * B + 1][0], T[2 * B + 1][1]), pack_bf(T[2 * B + 1][2], T[2 * B + 1][3]));
  }
}

__device__ __forceinline__ void feat(const float (&acc)[48], int j0, const uint32_t (&wf)[4], uint32_t* w) {
  const uint32_t a0 = pack_bf(acc[4 * j0], acc[4 * j0 + 1]), a1 = pack_bf(acc[4 * j0 + 2], acc[4 * j0 + 3]);
  const uint32_t a2 = pack_bf(acc[4 * j0 + 4], acc[4 * j0 + 5]), a3 = pack_bf(acc[4 * j0 + 6], acc[4 * j0 + 7]);
  float p[8];
  mma0(p[0], p[1], p[2], p[3], a0, a1, a2, a3, wf[0], wf[1]);
  mma0(p[4], p[5], p[6], p[7], a0, a1, a2, a3, wf[2], wf[3]);
  w[0] = pack_bf(p[0], p[2]); w[1] = pack_bf(p[1], p[3]); w[2] = pack_bf(p[4], p[6]); w[3] = pack_bf(p[5], p[7]);
}
__device__ __forceinline__ void dual_exp(const uint32_t* w, uint32_t* e) {
  const float L = 1.44268798828125f;
  uint32_t mx = bmax2(bmax2(w[0], w[1]), bmax2(w[2], w[3]));
  uint32_t mn = bmin2(bmin2(w[0], w[1]), bmin2(w[2], w[3]));
  mx = bmax2(mx, __shfl_xor_sync(0xffffffffu, mx, 1));
  mn = bmin2(mn, __shfl_xor_sync(0xffffffffu, mn, 1));
  mx = bmax2(mx, __shfl_xor_sync(0xffffffffu, mx, 2));
  mn = bmin2(mn, __shfl_xor_sync(0xffffffffu, mn, 2));
  const float mx0 = bf_lo(mx) * -L, mx1 = bf_hi(mx) * -L, mn0 = bf_lo(mn) * L, mn1 = bf_hi(mn) * L;
#pragma unroll
  for (int i = 0; i < 2; i++) {
    const float a0 = bf_lo(w[2 * i]), a1 = bf_hi(w[2 * i]), b0 = bf_lo(w[2 * i + 1]), b1 = bf_hi(w[2 * i + 1]);
    e[2 * i] = pack_bf(ex2(fmaf(a0, L, mx0)), ex2(fmaf(b0, L, mx0)));
    e[2 * i + 1] = pack_bf(ex2(fmaf(a1, L, mx1)), ex2(fmaf(b1, L, mx1)));
    e[4 + 2 * i] = pack_bf(ex2(fmaf(a0, -L, mn0)), ex2(fmaf(b0, -L, mn0)));
    e[5 + 2 * i] = pack_bf(ex2(fmaf(a1, -L, mn1)), ex2(fmaf(b1, -L, mn1)));
  }
}
__device__ __forceinline__ void norm_store(const uint32_t* e, uint32_t dst) {
  float s[4];
  mma0(s[0], s[1], s[2], s[3], e[0], e[1], e[2], e[3], 0x3F803F80u, 0x3F803F80u);
  const uint32_t r = pack_bf(rcp(s[0]), rcp(s[2]));
  const __nv_bfloat162 rr = *(const __nv_bfloat162*)&r;
  uint32_t o[4];
#pragma unroll
  for (int i = 0; i < 4; i++) {
    const __nv_bfloat162 v = __hmul2(*(const __nv_bfloat162*)&e[i], (i & 1) ? __high2bfloat162(rr) : __low2bfloat162(rr));
    o[i] = *(const uint32_t*)&v;
  }
  stsm4(dst, o[0], o[1], o[2], o[3]);
}

__global__ void __launch_bounds__(NTHREADS, 1)
fused_kernel(const Params P, const __grid_constant__ CUtensorMap mx, const __grid_constant__ CUtensorMap mw,
             const __grid_constant__ CUtensorMap mo, const __grid_constant__ CUtensorMap mu,
             const __grid_constant__ CUtensorMap mout) {
  constexpr uint32_t sb = SB;
  const int tid = threadIdx.x, lane = tid & 31;
  const int warp = __shfl_sync(0xffffffffu, tid >> 5, 0);
  const int b = blockIdx.x, oct = b >> 3, i8 = b & 7;
  const int rt = oct < 8 ? oct : 15 - oct;
  const int hp = (oct >> 3) * 8 + i8;

  const int d = b * 4 + ((tid >> 5) & 3);
  KgenRaw raw = {}, raw3 = {};
  unsigned short dsk = 0;
  if (tid < 384) {
    asm volatile("prefetch.tensormap [%0];" ::"l"(&mu) : "memory");
    asm volatile("prefetch.tensormap [%0];" ::"l"(&mw) : "memory");
    asm volatile("prefetch.tensormap [%0];" ::"l"(&mx) : "memory");
    raw = kgen_load(P, d, tid >> 7, lane);
    raw3 = kgen_load(P, d, 3, lane);
    dsk = __ldg((const unsigned short*)P.Dskip + d);
  }
  if (warp >= 12) asm volatile("setmaxnreg.dec.sync.aligned.u32 32;");
  if (warp == 12) {
    if (lane == 0) {
#pragma unroll
      for (int i = 0; i < 9; i++) mbar_init(BAR(i), 1);
      asm volatile("fence.mbarrier_init.release.cluster;" ::: "memory");
    }
    __syncwarp();
    if (lane < 9) mbar_expect(BAR(0) + 8 * lane, lane == 0 ? 16384 : (lane < 8 ? 28672 : 29696));
    __syncwarp();
    nb_arrive(NB_PREP, 448);
#pragma unroll 1
    for (int kb = 0; kb < 8; kb++) {
      if (kb == STEP_U) e_tma5d(sb + OFF_STG0, &mu, BAR(MB_URAW), i8 * 64, oct * 4);
      e_tma3d(sb + OFF_W + kb * 12288, &mw, BAR(MB_FULL) + 8 * kb, hp * 32, kb * 64, 0);
      if (kb < 5) e_tma2d(sb + OFF_X + (kb < 2 ? kb + 3 : kb - 2) * 16384, &mx, BAR(MB_FULL) + 8 * kb, kb * 64, rt * 256);
    }
    if (smem_u32(smem_raw) != SB) __trap();
  }
  if (warp >= 12) {
    if (warp == 12) {
      nb_sync(NB_PROD, 64);
      e_prefetch(P.x + (size_t)(rt * 256 + hp * 16) * 512, 16384);
      e_bulk(sb + OFF_PHI, P.wphi + hp * 512, 1024, BAR(MB_FULL + 7));
      uint32_t slot = sb + OFF_X + 3 * 16384;
#pragma unroll 1
      for (int n = 0; n < 11; n++) {
        mbar_wait(BAR(MB_EMPTY) + 8 * n);
        const int m = n + 5;
        e_tma2d(slot, &mx, BAR(MB_FULL) + 8 * m, (m & 7) * 64, rt * 256 + (m >> 3) * 128);
        slot = slot == sb + OFF_X + 4 * 16384 ? sb + OFF_X : slot + 16384;
        if (n == 7) e_prefetch(P.wo + (size_t)b * 2048, 4096);
      }
#pragma unroll 1
      for (int i = 0; i < 8; i++) {
        mbar_wait(BAR(MB_EMPTY + 10) + 8 * ((0x54332100u >> (4 * i)) & 7));
        const int w0 = (0x54736210u >> (4 * i)) & 7;
        e_tma3d(sb + OFF_W + w0 * 16384, &mo, BAR(MB_WO), 0, w0 * 64, (hp & 3) * 2);
      }
    } else {
      if (warp == 13) {
        if (lane == 0) {
#pragma unroll
          for (int i = 9; i < 39; i++) mbar_init(BAR(i), i < MB_EMPTY ? 1 : (i < MB_CLOSE ? 4 : 12));
          asm volatile("fence.mbarrier_init.release.cluster;" ::: "memory");
        }
        __syncwarp();
        if (lane < 9) mbar_expect(BAR(MB_FULL + 8) + 8 * lane, lane < 8 ? 16384 : 131072);
        __syncwarp();
        nb_arrive(NB_PROD, 64);
        nb_arrive(NB_PREP, 448);
      }
      nb_sync(NB_ZERO, 96);
      if (warp == 15) {
        mbar_wait(BAR(MB_EMPTY + ZERO_STEP));
        uint4* py = P.xs + X_Y + b * 1024 + lane;
#pragma unroll 1
        for (int i = 0; i < 1024; i += 32) st_x(py + i, 0, 0, 0, 0);
        nb_arrive(NB_YZ, 160);
        nb_arrive(NB_ODONE, 320);
        if (lane == 0) TS1(55);
        return;
      }
      uint32_t* const cnt = (uint32_t*)(P.xs + X_CNT) + (warp == 13 ? i8 : 8 + rt) * 32;
      const unsigned target = (ld_x32(cnt) & ~15u) + 16;
      if (warp == 13) {
        uint4* pp = P.xs + X_PART + (hp * 8 + rt) * 144 + lane;
#pragma unroll 1
        for (int i = 0; i < 144; i += 32) if (i + lane < 144) st_x(pp + i, 0, 0, 0, 0);
      }
      nb_sync(warp == 13 ? NB_INIT : NB_ODONE, warp == 13 ? 160 : 320);
      if (lane == 0) TS1(warp == 13 ? 49 : 56);
      asm volatile("fence.proxy.async.shared::cta;" ::: "memory");
      if (lane == 0) asm volatile("red.release.gpu.global.add.u32 [%0], 1;" ::"l"(cnt) : "memory");
      if (lane == 0) TS1(warp == 13 ? 50 : 57);
      const uint32_t* pc = (warp == 13 && (lane & 1)) ? (uint32_t*)(P.xs + X_CNT) + (b >> 4) * 32 : cnt;
#pragma unroll 1
      for (int i = 0; i < SPIN_MAX; i++) {
        unsigned v;
        asm volatile("ld.acquire.gpu.global.u32 %0, [%1];" : "=r"(v) : "l"(pc) : "memory");
        if (__all_sync(0xffffffffu, (int)(v - target) >= 0)) break;
      }
      if (lane == 0) TS1(warp == 13 ? 51 : 58);
      asm volatile("fence.proxy.async.global;" ::: "memory");
      if (warp == 13) {
        mbar_wait(BAR(MB_EMPTY + 11));
        e_expect(BAR(MB_UFULL), 4 * U_CH);
        e_bulk(sb + OFF_U, P.xs + X_UT + b * (U_CH / 4), 4 * U_CH, BAR(MB_UFULL));
      } else {
        const uint4* src = P.xs + X_O + (rt * 4 + (hp >> 2)) * 4096;
        e_expect(BAR(MB_OA), 14336);
        e_bulk(sb + OFF_STG0, src + 3200, 14336, BAR(MB_OA));
        e_expect(BAR(MB_OC), 32768);
        e_bulk(sb + OFF_X + 32768, src, 32768, BAR(MB_OC));
        nb_sync(NB_BDONE, 288);
        asm volatile("fence.proxy.async.shared::cta;" ::: "memory");
        e_expect(BAR(MB_OB), 18432);
        e_bulk(sb + OFF_U, src + 2048, 18432, BAR(MB_OB));
      }
    }
    return;
  }

  asm volatile("setmaxnreg.inc.sync.aligned.u32 160;");
  const int wg = warp >> 2, w = warp & 3, t = tid & 127;
  const int g = lane >> 2, c = lane & 3;
  const uint32_t tb = sb + OFF_T + w * T_CH;
  {
    float k[5][4], k2048 = 0.f, dt;
#pragma unroll
    for (int j = 0; j < 5; j++) k[j][0] = k[j][1] = k[j][2] = k[j][3] = 0.f;
    const uint32_t kp = tb + (wg & 1) * 2608;
#pragma unroll 1
    for (int r = 0; r <= (wg >> 1); r++) {
      kgen_unit(raw, lane, wg == 2 ? sb + OFF_STG0 + 16384 + w * 2048 : (kp + 127) & ~127u, r ? BAR(MB_EMPTY + 7) : 0u, dt, k, k2048);
      raw = raw3;
      TS(40 + wg + r);
      if (r == 0) {
        if (wg != 2) {
#pragma unroll
          for (int j = 0; j < 5; j++) sts128(kp + j * 512 + lane * 16, fu(k[j][0]), fu(k[j][1]), fu(k[j][2]), fu(k[j][3]));
          k2048 += __shfl_xor_sync(0xffffffffu, k2048, 16);
          k2048 += __shfl_xor_sync(0xffffffffu, k2048, 8);
          if (lane < 8) sts32(kp + 2560 + lane * 4, fu(k2048));
        } else if ((fu(k[0][0]) & fu(k[1][0]) & fu(k[2][0]) & fu(k[3][0]) & fu(k[4][0])) == 0xffffffffu) {
          sts32(kp, 0);
        }
        nb_sync(NB_PREP, 448);
        if (wg == 2) {
#pragma unroll 1
          for (int q = 0; q < 2; q++) {
            const uint32_t src = tb + q * 2608;
#pragma unroll
            for (int j = 0; j < 5; j++) {
              const uint4 v = lds128(src + j * 512 + lane * 16);
              k[j][0] += uf(v.x); k[j][1] += uf(v.y); k[j][2] += uf(v.z); k[j][3] += uf(v.w);
            }
            if (lane < 8) k2048 += uf(lds32(src + 2560 + lane * 4));
          }
        }
      }
    }
    if (wg == 2) {
      if (lane == 0 && (fu(k[0][0]) & fu(k[1][0]) & fu(k[2][0]) & fu(k[3][0]) & fu(k[4][0])) != 0xffffffffu)
        mbar_arrive(BAR(MB_CLOSE));
      TS(34);
#pragma unroll
      for (int o2 = 16; o2; o2 >>= 1) k2048 += __shfl_xor_sync(0xffffffffu, k2048, o2);
      const float sc = 2.f * dt;
#pragma unroll
      for (int j = 0; j < 5; j++) { k[j][0] *= sc; k[j][1] *= sc; k[j][2] *= sc; k[j][3] *= sc; }
      k2048 *= sc;
      if (lane == 0) k[0][0] += bf_lo(dsk);
      build_tables(tb, lane, k, k2048);
      TS(35);
      nb_sync(NB_YZ, 160);
      mbar_wait(BAR(MB_UFULL));
      uint4* const g_y = P.xs + X_Y;
      conv_channel(sb + OFF_U + w * U_CH, tb, lane, g_y + (size_t)d * 256 + lane);
      nb_arrive(NB_BDONE, 288);
      TS(37);
      mbar_wait(BAR(MB_OA));
      const int lam = w * 8 + g;
      const uint4* src = g_y + (size_t)(oct * 32 + c * 8) * 256 + i8 * 32 + lam;
      uint4 v[8];
#pragma unroll 1
      for (int it = 0; it < SPIN_MAX; it++) {
        uint32_t m = 0xffffffffu;
#pragma unroll
        for (int i = 0; i < 8; i++) v[i] = ld_x(src + i * 256);
#pragma unroll
        for (int i = 0; i < 8; i++) m = min(m, v[i].x);
        if (__all_sync(0xffffffffu, m != 0)) break;
      }
      __nv_bfloat16* dst = P.out + (size_t)(i8 * 256 + (lam >> 2) * 16 + (lam & 3) * 2) * 1024 + 512 + oct * 32 + c * 8;
#pragma unroll
      for (int i = 0; i < 8; i++) *(uint4*)(dst + (size_t)((i >> 2) * 128 + ((i >> 1) & 1) * 8 + (i & 1)) * 1024) = tr_row(v, i);
      TS(38);
      GT(63);
      return;
    }
    if (wg == 1) {
      mbar_wait(BAR(MB_URAW));
      TS(48);
      uint4* dst = P.xs + X_UT + (i8 * 64 + g) * (U_CH / 16) + (c & 1) * (U_ODD / 16) + U_PAD / 16 + oct * 8 + w * 2 + (c >> 1);
      uint32_t r[8][4];
#pragma unroll
      for (int i = 0; i < 8; i++) ldsm4t(r[i], sb + OFF_STG0 + w * 4096 + lane * 128 + (((i ^ lane) & 7) << 4));
#pragma unroll
      for (int i = 0; i < 8; i++) dst[i * (U_CH / 2)] = make_uint4(r[i][0], r[i][1], r[i][2], r[i][3]);
      nb_arrive(NB_INIT, 160);
      if (lane == 0) mbar_arrive(BAR(MB_CLOSE));
      mbar_wait(BAR(MB_CLOSE));
    }
    TS(wg * 16 + 1);
  }

  float acc[2][48];
  {
    uint32_t fb = BAR(MB_FULL) + 64 * wg;
    uint32_t da = (uint32_t)mkdesc(sb + OFF_X, 16, 0, 0) + (wg ? 1024 : 3072), db = (uint32_t)mkdesc(sb + OFF_W, 4096, 0, 0);
    constexpr uint64_t ha = mkdesc(0, 0, 1024, 1), hb = mkdesc(0, 0, 512, 2);
#pragma unroll 1
    for (int kb = 0; kb < 8; kb++) {
      mbar_wait(fb);
      if (kb == 0) TS(wg * 16 + 2);
      WG_FENCE();
#pragma unroll
      for (int k = 0; k < 4; k++) {
        wgmma_ss_n96(acc[0], ha | (da + 2 * k), hb | (db + 64 * k), k ? 1 : kb);
        wgmma_ss_n96(acc[1], ha | (da + 2 * k + 512), hb | (db + 64 * k), k ? 1 : kb);
      }
      WG_COMMIT();
      WG_WAIT(1);
      if (kb > 0 && lane == 0) mbar_arrive(fb + 8 * (MB_EMPTY - MB_FULL - 1));
      fb += 8; db += 768;
      da = da == (uint32_t)mkdesc(sb + OFF_X + 65536, 16, 0, 0) ? da - 4096 : da + 1024;
    }
    WG_WAIT(0);
    if (lane == 0) mbar_arrive(fb + 8 * (MB_EMPTY - MB_FULL - 1));
    mbar_wait(fb + 8 * (MB_EMPTY - MB_FULL - 1));
  }
  uint32_t wf[2][4];
  ldsm4t(wf[0], sb + OFF_PHI + (lane & 15) * 32 + (lane >> 4) * 16);
  ldsm4t(wf[1], sb + OFF_PHI + 512 + (lane & 15) * 32 + (lane >> 4) * 16);
  TS(wg * 16 + 3);

  uint32_t pw[32], eq[32];
#pragma unroll
  for (int u = 0; u < 4; u++)
#pragma unroll
    for (int h = 0; h < 2; h++) feat(acc[u & 1], (u < 2 ? 4 : 0) + 2 * h, wf[h], pw + 8 * u + 4 * h);
  {
    uint32_t all = 0xffffffffu;
#pragma unroll
    for (int i = 0; i < 16; i++) all &= pw[2 * i];
    if (wg == 0 && lane == 0 && all != 0xffffffffu) mbar_arrive(BAR(MB_CLOSE));
  }
  mbar_wait(BAR(MB_CLOSE));
  constexpr uint32_t stg0 = sb + OFF_STG0, stg1 = sb + OFF_X + 32768;
  const uint32_t sl = (wg ? stg1 : stg0) + w * 3072 + lane * 16;
#pragma unroll
  for (int mt = 0; mt < 2; mt++)
#pragma unroll
    for (int h = 0; h < 2; h++) {
      const float* a = acc[mt] + 32 + 8 * h;
      stsm4(sl + mt * 12288 + 2048 + h * 512, pack_bf(a[0], a[1]), pack_bf(a[2], a[3]), pack_bf(a[4], a[5]), pack_bf(a[6], a[7]));
    }
  uint32_t ek[32];
  if (wg == 0) {
#pragma unroll
    for (int i = 0; i < 16; i++) { const uint32_t x = pw[i]; pw[i] = pw[16 + i]; pw[16 + i] = x; }
  }
#pragma unroll 1
  for (int it = 0; it < 2; it++) {
#pragma unroll
    for (int i = 0; i < 32; i++) ek[i] = eq[i];
#pragma unroll
    for (int u = 0; u < 4; u++) dual_exp(pw + 4 * u, eq + 8 * u);
    if (it != wg) {
      TS(wg * 16 + 12);
      mbar_wait(BAR(MB_EMPTY + 15));
#pragma unroll
      for (int i = 0; i < 8; i++) norm_store(eq + 4 * i, sl + (i >> 2) * 12288 + (i & 3) * 512);
      if (wg) nb_arrive(NB_ST0, 256);
    }
#pragma unroll
    for (int i = 0; i < 16; i++) pw[i] = pw[i + 16];
  }
  TS(wg * 16 + 4);
  uint4* const g_part = P.xs + X_PART;
  uint4* const g_o = P.xs + X_O;
  const uint32_t kvs = stg0;
  if (wg == 0) {
#pragma unroll
    for (int i = 0; i < 32; i++) eq[i] = ek[i];
    nb_sync(NB_WG0, 128);
    mbar_wait(BAR(MB_UFULL));
    float kv[12];
#pragma unroll
    for (int i = 0; i < 12; i++) kv[i] = 0.f;
    const int mi = lane >> 3;
    const uint32_t ao = w * 512 + (lane & 7) * 16 + ((mi & 1) * 2 + (mi >> 1)) * 128, bo = 2048 + (w >> 1) * 512 + lane * 16;
#pragma unroll 1
    for (int j = 0; j < 4; j++) {
      if (j == 2) nb_sync(NB_ST0, 256);
      const uint32_t sg = (j >= 2 ? stg1 : stg0) + (j & 1) * 12288;
      uint32_t a[4][4], bb[4][4];
#pragma unroll
      for (int s = 0; s < 4; s++) { ldsm4t(a[s], sg + s * 3072 + ao); ldsm4t(bb[s], sg + s * 3072 + bo); }
#pragma unroll
      for (int s = 0; s < 4; s++) {
        mma(kv[0], kv[1], kv[2], kv[3], a[s][0], a[s][1], a[s][2], a[s][3], bb[s][0], bb[s][1]);
        mma(kv[4], kv[5], kv[6], kv[7], a[s][0], a[s][1], a[s][2], a[s][3], bb[s][2], bb[s][3]);
        mma(kv[8], kv[9], kv[10], kv[11], a[s][0], a[s][1], a[s][2], a[s][3], 0x3F803F80u, 0x3F803F80u);
      }
    }
    uint4* pp = g_part + (size_t)(hp * 8 + rt) * 144;
    st_x(pp + t, nz(pack_bf(kv[0], kv[1])), pack_bf(kv[2], kv[3]), pack_bf(kv[4], kv[5]), pack_bf(kv[6], kv[7]));
    if (c < 2) st_x32((uint32_t*)(pp + 128) + w * 16 + c * 8 + g, nz(fu(c ? kv[10] : kv[8])));
    TS(5);
    const uint4* ps = g_part + (size_t)hp * 8 * 144 + t;
    const uint32_t* zs = (const uint32_t*)(g_part + (size_t)(hp * 8 + (lane >> 4) * 4) * 144 + 128) + w * 16 + (lane & 15);
    uint4 v[8];
    uint32_t zv[4];
#pragma unroll 1
    for (int it = 0; it < SPIN_MAX; it++) {
#pragma unroll
      for (int i = 0; i < 8; i++) v[i] = ld_x(ps + i * 144);
#pragma unroll
      for (int i = 0; i < 4; i++) zv[i] = ld_x32(zs + i * 576);
      uint32_t m = min(min(zv[0], zv[1]), min(zv[2], zv[3]));
#pragma unroll
      for (int i = 0; i < 8; i++) m = min(m, v[i].x);
      if (__all_sync(0xffffffffu, m != 0)) break;
    }
    float s4[4][4];
#pragma unroll
    for (int i = 0; i < 4; i++) s4[i][0] = s4[i][1] = s4[i][2] = s4[i][3] = 0.f;
    const uint32_t eye = (g >> 1) == c ? ((g & 1) ? 0x3F800000u : 0x3F80u) : 0u;
#pragma unroll
    for (int r = 0; r < 8; r++) {
      mma_k8(s4[(r & 1) * 2], v[r].x, v[r].y, eye);
      mma_k8(s4[(r & 1) * 2 + 1], v[r].z, v[r].w, eye);
    }
    float s[8];
#pragma unroll
    for (int i = 0; i < 8; i++) s[i] = s4[i >> 2][i & 3] + s4[2 + (i >> 2)][i & 3];
    float zsum = (uf(zv[0]) + uf(zv[1])) + (uf(zv[2]) + uf(zv[3]));
    zsum += __shfl_xor_sync(0xffffffffu, zsum, 16);
    stsm4(kvs + w * 512 + lane * 16, pack_bf(s[0], s[1]), pack_bf(s[2], s[3]), pack_bf(s[4], s[5]), pack_bf(s[6], s[7]));
    sts16(kvs + 2048 + (lane >> 4) * 128 + (w * 16 + (lane & 15)) * 2, lane < 16 ? pack_bf(zsum, 0.f) : 0x3F80u);
    TS(6);
  }
  nb_sync(NB_KV, 256);
  {
    uint32_t kb_[4][4], zb[8];
#pragma unroll
    for (int i = 0; i < 4; i++) ldsm4t(kb_[i], kvs + i * 512 + lane * 16);
#pragma unroll
    for (int i = 0; i < 8; i++) zb[i] = lds32(kvs + 2048 + (g & 1) * 128 + i * 16 + c * 4);
    uint32_t* od = (uint32_t*)(g_o + (size_t)((rt * 4 + wg * 2) * 32 + hp * 2) * 128) + w * 64 + lane;
#pragma unroll 1
    for (int mt = 0; mt < 2; mt++) {
#pragma unroll
      for (int h = 0; h < 2; h++) {
        const uint32_t* e = eq + 8 * h;
        float n[8], nm[8], dp[4], dm[4];
        mma0(dp[0], dp[1], dp[2], dp[3], e[0], e[1], e[2], e[3], zb[4 * h], zb[4 * h + 1]);
        mma0(dm[0], dm[1], dm[2], dm[3], e[4], e[5], e[6], e[7], zb[4 * h + 2], zb[4 * h + 3]);
        mma0(n[0], n[1], n[2], n[3], e[0], e[1], e[2], e[3], kb_[2 * h][0], kb_[2 * h][1]);
        mma0(nm[0], nm[1], nm[2], nm[3], e[4], e[5], e[6], e[7], kb_[2 * h + 1][0], kb_[2 * h + 1][1]);
        mma0(n[4], n[5], n[6], n[7], e[0], e[1], e[2], e[3], kb_[2 * h][2], kb_[2 * h][3]);
        mma0(nm[4], nm[5], nm[6], nm[7], e[4], e[5], e[6], e[7], kb_[2 * h + 1][2], kb_[2 * h + 1][3]);
        const float q0 = dp[1] * rcp(dm[1]), q1 = dp[3] * rcp(dm[3]);
        const float r0 = rcp(fmaf(dm[0], q0, fmaf(dp[1], 1e-6f, dp[0]))), r1 = rcp(fmaf(dm[2], q1, fmaf(dp[3], 1e-6f, dp[2])));
#pragma unroll
        for (int i = 0; i < 8; i++) n[i] = fmaf(nm[i], (i & 2) ? q1 : q0, n[i]);
        od[h * 512] = pack_bf(n[0] * r0, n[1] * r0);
        od[h * 512 + 32] = pack_bf(n[2] * r1, n[3] * r1);
        od[h * 512 + 256] = pack_bf(n[4] * r0, n[5] * r0);
        od[h * 512 + 288] = pack_bf(n[6] * r1, n[7] * r1);
      }
#pragma unroll
      for (int i = 0; i < 16; i++) eq[i] = eq[16 + i];
      od += 16384;
    }
  }
  TS(wg * 16 + 7);
  nb_arrive(NB_ODONE, 320);
  if (wg) return;
  mbar_wait(BAR(MB_WO));
  mbar_wait(BAR(MB_OA));
  TS(8);
  nb_sync(NB_BDONE, 288);
  TS(9);
  float oc[64];
  {
    constexpr uint64_t ha = mkdesc(0, 0, 128, 0), hb = mkdesc(0, 0, 1024, 1);
    constexpr uint32_t da0 = (uint32_t)mkdesc(stg1, 1024, 0, 0), db0 = (uint32_t)mkdesc(sb + OFF_W, 8192, 0, 0);
#pragma unroll 1
    for (int j = 0; j < 8; j++) {
      const int kb = (j + 7) & 7;
      if ((j & 3) == 1) mbar_wait(j == 1 ? BAR(MB_OC) : BAR(MB_OB));
      WG_FENCE();
#pragma unroll
      for (int k = 0; k < 4; k++) wgmma_ss_n128(oc, ha | (da0 + 512 * kb + 128 * k), hb | (db0 + 1024 * kb + 128 * k), k ? 1 : j);
      WG_COMMIT();
    }
    WG_WAIT(0);
  }
  TS(10);
  nb_sync(NB_WG0, 128);
  const uint32_t ot = sb + OFF_W + w * 4096;
#pragma unroll
  for (int i = 0; i < 16; i += 2)
    stsm4(ot + (i >> 3) * 2048 + (lane & 15) * 128 + (((i + (lane >> 4)) ^ lane) & 7) * 16, pack_bf(oc[4 * i], oc[4 * i + 1]),
          pack_bf(oc[4 * i + 2], oc[4 * i + 3]), pack_bf(oc[4 * i + 4], oc[4 * i + 5]), pack_bf(oc[4 * i + 6], oc[4 * i + 7]));
  asm volatile("fence.proxy.async.shared::cta;" ::: "memory");
  __syncwarp();
  e_store3d(&mout, ot, (rt * 4 + (hp >> 2)) * 64 + w * 16, (hp & 3) * 2);
  TS(wg * 16 + 11);
  GT(61 + wg);
}

typedef CUresult (*EncodeFn)(CUtensorMap*, CUtensorMapDataType, cuuint32_t, void*, const cuuint64_t*, const cuuint64_t*,
                             const cuuint32_t*, const cuuint32_t*, CUtensorMapInterleave, CUtensorMapSwizzle,
                             CUtensorMapL2promotion, CUtensorMapFloatOOBfill);

}

extern "C" void kernel_launch(void* const* d_in, const int* in_sizes, int n_in, void* d_out, int out_size) {
  (void)in_sizes; (void)n_in; (void)out_size;
  void* fn = nullptr;
  cudaDriverEntryPointQueryResult qr;
  cudaGetDriverEntryPoint("cuTensorMapEncodeTiled", &fn, cudaEnableDefault, &qr);
  EncodeFn enc = (EncodeFn)fn;
  CUtensorMap mx, mw, mo, mu, mout;
  const cuuint32_t es[5] = {1, 1, 1, 1, 1};
  {
    cuuint64_t dims[2] = {512, 2048}, st[1] = {1024};
    cuuint32_t box[2] = {64, 128};
    enc(&mx, CU_TENSOR_MAP_DATA_TYPE_BFLOAT16, 2, d_in[0], dims, st, box, es, CU_TENSOR_MAP_INTERLEAVE_NONE,
        CU_TENSOR_MAP_SWIZZLE_128B, CU_TENSOR_MAP_L2_PROMOTION_L2_128B, CU_TENSOR_MAP_FLOAT_OOB_FILL_NONE);
  }
  {
    cuuint64_t dims[3] = {512, 512, 3}, st[2] = {3072, 1024};
    cuuint32_t box[3] = {32, 64, 3};
    enc(&mw, CU_TENSOR_MAP_DATA_TYPE_BFLOAT16, 3, d_in[1], dims, st, box, es, CU_TENSOR_MAP_INTERLEAVE_NONE,
        CU_TENSOR_MAP_SWIZZLE_64B, CU_TENSOR_MAP_L2_PROMOTION_L2_128B, CU_TENSOR_MAP_FLOAT_OOB_FILL_NONE);
  }
  {
    cuuint64_t dims[3] = {64, 512, 8}, st[2] = {1024, 128};
    cuuint32_t box[3] = {64, 64, 2};
    enc(&mo, CU_TENSOR_MAP_DATA_TYPE_BFLOAT16, 3, d_in[3], dims, st, box, es, CU_TENSOR_MAP_INTERLEAVE_NONE,
        CU_TENSOR_MAP_SWIZZLE_128B, CU_TENSOR_MAP_L2_PROMOTION_L2_128B, CU_TENSOR_MAP_FLOAT_OOB_FILL_NONE);
  }
  {
    cuuint64_t dims[5] = {512, 2, 4, 4, 64}, st[4] = {1024, 8192, 2048, 32768};
    cuuint32_t box[5] = {64, 2, 4, 4, 4};
    enc(&mu, CU_TENSOR_MAP_DATA_TYPE_BFLOAT16, 5, d_in[4], dims, st, box, es, CU_TENSOR_MAP_INTERLEAVE_NONE,
        CU_TENSOR_MAP_SWIZZLE_128B, CU_TENSOR_MAP_L2_PROMOTION_L2_128B, CU_TENSOR_MAP_FLOAT_OOB_FILL_NONE);
  }
  {
    cuuint64_t dims[3] = {64, 2048, 16}, st[2] = {2048, 128};
    cuuint32_t box[3] = {64, 16, 2};
    enc(&mout, CU_TENSOR_MAP_DATA_TYPE_BFLOAT16, 3, d_out, dims, st, box, es, CU_TENSOR_MAP_INTERLEAVE_NONE,
        CU_TENSOR_MAP_SWIZZLE_128B, CU_TENSOR_MAP_L2_PROMOTION_NONE, CU_TENSOR_MAP_FLOAT_OOB_FILL_NONE);
  }
  Params P;
  P.x = (const __nv_bfloat16*)d_in[0];
  P.wphi = (const __nv_bfloat16*)d_in[2];
  P.wo = (const __nv_bfloat16*)d_in[3];
  P.logA = (const __nv_bfloat16*)d_in[5];
  P.Aim = (const __nv_bfloat16*)d_in[6];
  P.Cre = (const __nv_bfloat16*)d_in[7];
  P.Cim = (const __nv_bfloat16*)d_in[8];
  P.logdt = (const __nv_bfloat16*)d_in[9];
  P.Dskip = (const __nv_bfloat16*)d_in[10];
  P.out = (__nv_bfloat16*)d_out;
  cudaGetSymbolAddress((void**)&P.xs, g_x);
  P.ts = nullptr;
  cudaFuncSetAttribute(fused_kernel, cudaFuncAttributeMaxDynamicSharedMemorySize, SMEM_BYTES);
  fused_kernel<<<NCTA, NTHREADS, SMEM_BYTES>>>(P, mx, mw, mo, mu, mout);
}
```

```cpp
#include <cuda_runtime.h>
#include <cuda_bf16.h>
#include <cuda.h>
#include <stdint.h>

#define DBG_TS 0

namespace {

constexpr int NTHREADS = 512;
constexpr int NCTA = 128;
constexpr int OFF_W = 0;
constexpr int OFF_X = 98304;
constexpr int OFF_U = OFF_X + 65536;
constexpr int U_CH = 4416, U_ODD = 2240, U_PAD = 128;
constexpr int OFF_STG0 = OFF_U + 18432;
constexpr int OFF_T = OFF_STG0 + 24576;
constexpr int T_CH = 5216;
constexpr int T_D = 0;
constexpr int T_5 = 2144;
constexpr int T_3 = T_5 + 384;
constexpr int T_7 = T_5 + 1024;
constexpr int T_9 = T_7 + 320;
constexpr int T_KC = T_9 + 320;
constexpr int T_ST = T_5 - 1024;
constexpr int OFF_PHI = OFF_T + 4 * T_CH;
constexpr int OFF_BAR = OFF_PHI + 1024;
constexpr int SMEM_BYTES = OFF_BAR + 512;
constexpr uint32_t SB = 1024;
static_assert(T_KC + 2 * 656 <= T_CH, "table size");
static_assert(SMEM_BYTES <= 232448, "smem");
constexpr int MB_URAW = 0, MB_FULL = 1  , MB_WO = 17, MB_UFULL = 18, MB_OA = 19, MB_OB = 20, MB_OC = 21,
              MB_EMPTY = 22  , MB_AUX = 38;
__host__ __device__ constexpr uint32_t BAR(int i) { return SB + OFF_BAR + 8 * i; }
constexpr int NB_WG0 = 1, NB_ODONE = 2, NB_ST0 = 3  , NB_KV = 5, NB_YZ = 6, NB_INIT = 7, NB_PREP = 8, NB_PROD = 9, NB_RDY = 10, NB_BDONE = 11, NB_ZERO = 12;
#define ZERO_N 1024
#define ZERO_STEP 7
#define STEPU 3
#define STEPPF 0
constexpr int STEP_PF = STEPPF, STEP_U = STEPU;
constexpr int SPIN_MAX = 1 << 16;

constexpr int X_CNT = 0;
constexpr int X_PART = 128;
constexpr int X_O = X_PART + 16 * 8 * 144;
constexpr int X_Y = X_O + 32 * 32 * 128;
constexpr int X_UT = X_Y + 512 * 8 * 32;
constexpr int X_SIZE = X_UT + 512 * (U_CH / 16);
__device__ __align__(128) uint4 g_x[X_SIZE];
extern __shared__ uint8_t smem_raw[];
#define TS(i) do {} while (0)
#define TS1(i) do {} while (0)
#define GT(i) do {} while (0)

__device__ __forceinline__ uint32_t smem_u32(const void* p) { return (uint32_t)__cvta_generic_to_shared(p); }
__device__ __forceinline__ void mbar_arrive(uint32_t b) {
  asm volatile("mbarrier.arrive.shared::cta.b64 _, [%0];" ::"r"(b) : "memory");
}
__device__ __forceinline__ void mbar_wait(uint32_t b) {
  uint32_t done = 0;
#pragma unroll 1
  for (int i = 0; i < SPIN_MAX && !done; i++) {
    asm volatile("{\n.reg .pred p;\nmbarrier.try_wait.parity.shared::cta.b64 p, [%1], 0, 4000;\nselp.u32 %0, 1, 0, p;\n}\n"
                 : "=r"(done) : "r"(b) : "memory");
  }
}
__device__ __forceinline__ void mbar_init(uint32_t b, int n) {
  asm volatile("mbarrier.init.shared::cta.b64 [%0], %1;" ::"r"(b), "r"(n) : "memory");
}
__device__ __forceinline__ void mbar_expect(uint32_t b, int bytes) {
  asm volatile("mbarrier.arrive.expect_tx.shared::cta.b64 _, [%0], %1;" ::"r"(b), "r"(bytes) : "memory");
}
__device__ __forceinline__ void nb_sync(int id, int n) { asm volatile("bar.sync %0, %1;" ::"r"(id), "r"(n) : "memory"); }
__device__ __forceinline__ void nb_arrive(int id, int n) { asm volatile("bar.arrive %0, %1;" ::"r"(id), "r"(n) : "memory"); }
#define ELECT "{\n.reg .pred p;\nelect.sync _|p, 0xffffffff;\n@p "
__device__ __forceinline__ void e_expect(uint32_t b, int bytes) {
  asm volatile(ELECT "mbarrier.arrive.expect_tx.shared::cta.b64 _, [%0], %1;\n}\n" ::"r"(b), "r"(bytes) : "memory");
}
__device__ __forceinline__ void e_tma2d(uint32_t dst, const CUtensorMap* m, uint32_t bar, int c0, int c1) {
  asm volatile(ELECT "cp.async.bulk.tensor.2d.shared::cluster.global.mbarrier::complete_tx::bytes [%0], [%1, {%3,%4}], [%2];\n}\n"
               ::"r"(dst), "l"(m), "r"(bar), "r"(c0), "r"(c1) : "memory");
}
__device__ __forceinline__ void e_tma3d(uint32_t dst, const CUtensorMap* m, uint32_t bar, int c0, int c1, int c2) {
  asm volatile(ELECT "cp.async.bulk.tensor.3d.shared::cluster.global.mbarrier::complete_tx::bytes [%0], [%1, {%3,%4,%5}], [%2];\n}\n"
               ::"r"(dst), "l"(m), "r"(bar), "r"(c0), "r"(c1), "r"(c2) : "memory");
}
__device__ __forceinline__ void e_tma5d(uint32_t dst, const CUtensorMap* m, uint32_t bar, int c0, int c4) {
  asm volatile(ELECT "cp.async.bulk.tensor.5d.shared::cluster.global.mbarrier::complete_tx::bytes [%0], [%1, {%3,%5,%5,%5,%4}], [%2];\n}\n"
               ::"r"(dst), "l"(m), "r"(bar), "r"(c0), "r"(c4), "r"(0) : "memory");
}
__device__ __forceinline__ void e_bulk(uint32_t dst, const void* src, int bytes, uint32_t bar) {
  asm volatile(ELECT "cp.async.bulk.shared::cluster.global.mbarrier::complete_tx::bytes [%0], [%1], %2, [%3];\n}\n"
               ::"r"(dst), "l"(src), "r"(bytes), "r"(bar) : "memory");
}
__device__ __forceinline__ void e_prefetch(const void* p, int bytes) {
  asm volatile(ELECT "cp.async.bulk.prefetch.L2.global [%0], %1;\n}\n" ::"l"(p), "r"(bytes) : "memory");
}
__device__ __forceinline__ void e_store3d(const CUtensorMap* m, uint32_t src, int c1, int c2) {
  asm volatile(ELECT "cp.async.bulk.tensor.3d.global.shared::cta.bulk_group [%0, {%4,%2,%3}], [%1];\n"
               "@p cp.async.bulk.commit_group;\n@p cp.async.bulk.wait_group.read 0;\n}\n"
               ::"l"(m), "r"(src), "r"(c1), "r"(c2), "r"(0) : "memory");
}
__host__ __device__ constexpr uint64_t mkdesc(uint32_t addr, uint32_t lbo, uint32_t sbo, int swz) {
  return (uint64_t)((addr & 0x3FFFF) >> 4) | ((uint64_t)(lbo >> 4) << 16) | ((uint64_t)(sbo >> 4) << 32) |
         ((uint64_t)swz << 62);
}
#define WG_FENCE() asm volatile("wgmma.fence.sync.aligned;" ::: "memory")
#define WG_COMMIT() asm volatile("wgmma.commit_group.sync.aligned;" ::: "memory")
#define WG_WAIT(n) asm volatile("wgmma.wait_group.sync.aligned " #n ";" ::: "memory")

__device__ __forceinline__ void mma(float& d0, float& d1, float& d2, float& d3, uint32_t a0, uint32_t a1, uint32_t a2,
                                    uint32_t a3, uint32_t b0, uint32_t b1) {
  asm volatile("mma.sync.aligned.m16n8k16.row.col.f32.bf16.bf16.f32 {%0,%1,%2,%3},{%4,%5,%6,%7},{%8,%9},{%0,%1,%2,%3};"
               : "+f"(d0), "+f"(d1), "+f"(d2), "+f"(d3)
               : "r"(a0), "r"(a1), "r"(a2), "r"(a3), "r"(b0), "r"(b1));
}
__device__ __forceinline__ void mmac(float (&d)[4], uint32_t a0, uint32_t a1, uint32_t a2, uint32_t a3, uint32_t b0,
                                     uint32_t b1, const float (&c)[4]) {
  asm volatile("mma.sync.aligned.m16n8k16.row.col.f32.bf16.bf16.f32 {%0,%1,%2,%3},{%4,%5,%6,%7},{%8,%9},{%10,%11,%12,%13};"
               : "=f"(d[0]), "=f"(d[1]), "=f"(d[2]), "=f"(d[3])
               : "r"(a0), "r"(a1), "r"(a2), "r"(a3), "r"(b0), "r"(b1), "f"(c[0]), "f"(c[1]), "f"(c[2]), "f"(c[3]));
}
__device__ __forceinline__ void mma_p(int p, float (&d)[4], uint32_t a0, uint32_t a1, uint32_t a2, uint32_t a3, uint32_t b0, uint32_t b1) {
  asm volatile("{\n.reg .pred q;\nsetp.ne.b32 q, %10, 0;\n"
               "@q mma.sync.aligned.m16n8k16.row.col.f32.bf16.bf16.f32 {%0,%1,%2,%3},{%4,%5,%6,%7},{%8,%9},{%0,%1,%2,%3};\n}\n"
               : "+f"(d[0]), "+f"(d[1]), "+f"(d[2]), "+f"(d[3])
               : "r"(a0), "r"(a1), "r"(a2), "r"(a3), "r"(b0), "r"(b1), "r"(p));
}
__device__ __forceinline__ void mmac_p(int p, float (&d)[4], uint32_t a0, uint32_t a1, uint32_t a2, uint32_t a3, uint32_t b0,
                                       uint32_t b1, const float (&c)[4]) {
  asm volatile("{\n.reg .pred q;\nsetp.ne.b32 q, %14, 0;\n"
               "@q mma.sync.aligned.m16n8k16.row.col.f32.bf16.bf16.f32 {%0,%1,%2,%3},{%4,%5,%6,%7},{%8,%9},{%10,%11,%12,%13};\n}\n"
               : "+f"(d[0]), "+f"(d[1]), "+f"(d[2]), "+f"(d[3])
               : "r"(a0), "r"(a1), "r"(a2), "r"(a3), "r"(b0), "r"(b1), "f"(c[0]), "f"(c[1]), "f"(c[2]), "f"(c[3]), "r"(p));
}
__device__ __forceinline__ void mma_k8(float (&d)[4], uint32_t a0, uint32_t a1, uint32_t b0) {
  asm volatile("mma.sync.aligned.m16n8k8.row.col.f32.bf16.bf16.f32 {%0,%1,%2,%3},{%4,%5},{%6},{%0,%1,%2,%3};"
               : "+f"(d[0]), "+f"(d[1]), "+f"(d[2]), "+f"(d[3]) : "r"(a0), "r"(a1), "r"(b0));
}
__device__ __forceinline__ void mma0(float& d0, float& d1, float& d2, float& d3, uint32_t a0, uint32_t a1, uint32_t a2,
                                     uint32_t a3, uint32_t b0, uint32_t b1) {
  asm volatile("mma.sync.aligned.m16n8k16.row.col.f32.bf16.bf16.f32 {%0,%1,%2,%3},{%4,%5,%6,%7},{%8,%9},{%10,%10,%10,%10};"
               : "=f"(d0), "=f"(d1), "=f"(d2), "=f"(d3)
               : "r"(a0), "r"(a1), "r"(a2), "r"(a3), "r"(b0), "r"(b1), "f"(0.f));
}
__device__ __forceinline__ uint32_t pack_bf(float lo, float hi) {
  uint32_t r;
  asm("cvt.rn.bf16x2.f32 %0, %1, %2;" : "=r"(r) : "f"(hi), "f"(lo));
  return r;
}
__device__ __forceinline__ float bf_lo(uint32_t w) { return __uint_as_float(w << 16); }
__device__ __forceinline__ float bf_hi(uint32_t w) { return __uint_as_float(w & 0xffff0000u); }
__device__ __forceinline__ float bf_round(float x) { return __bfloat162float(__float2bfloat16_rn(x)); }
__device__ __forceinline__ uint32_t bmax2(uint32_t a, uint32_t b) {
  uint32_t r; asm("max.bf16x2 %0, %1, %2;" : "=r"(r) : "r"(a), "r"(b)); return r;
}
__device__ __forceinline__ uint32_t bmin2(uint32_t a, uint32_t b) {
  uint32_t r; asm("min.bf16x2 %0, %1, %2;" : "=r"(r) : "r"(a), "r"(b)); return r;
}
__device__ __forceinline__ float ex2(float x) { float r; asm("ex2.approx.ftz.f32 %0, %1;" : "=f"(r) : "f"(x)); return r; }
__device__ __forceinline__ float rcp(float x) { float r; asm("rcp.approx.ftz.f32 %0, %1;" : "=f"(r) : "f"(x)); return r; }
__device__ __forceinline__ void ldsm4(uint32_t (&r)[4], uint32_t a) {
  asm volatile("ldmatrix.sync.aligned.m8n8.x4.shared.b16 {%0,%1,%2,%3}, [%4];"
               : "=r"(r[0]), "=r"(r[1]), "=r"(r[2]), "=r"(r[3]) : "r"(a) : "memory");
}
__device__ __forceinline__ void ldsm4t(uint32_t (&r)[4], uint32_t a) {
  asm volatile("ldmatrix.sync.aligned.m8n8.x4.trans.shared.b16 {%0,%1,%2,%3}, [%4];"
               : "=r"(r[0]), "=r"(r[1]), "=r"(r[2]), "=r"(r[3]) : "r"(a) : "memory");
}
__device__ __forceinline__ void stsm4(uint32_t a, uint32_t r0, uint32_t r1, uint32_t r2, uint32_t r3) {
  asm volatile("stmatrix.sync.aligned.m8n8.x4.shared.b16 [%0], {%1,%2,%3,%4};"
               ::"r"(a), "r"(r0), "r"(r1), "r"(r2), "r"(r3) : "memory");
}
__device__ __forceinline__ uint32_t lds32(uint32_t a) {
  uint32_t r; asm volatile("ld.shared.u32 %0, [%1];" : "=r"(r) : "r"(a) : "memory"); return r;
}
__device__ __forceinline__ uint32_t lds16(uint32_t a) {
  uint32_t r; asm volatile("{\n.reg .u16 h;\nld.shared.u16 h, [%1];\ncvt.u32.u16 %0, h;\n}\n" : "=r"(r) : "r"(a) : "memory"); return r;
}
__device__ __forceinline__ uint2 lds64(uint32_t a) {
  uint2 r; asm volatile("ld.shared.v2.u32 {%0,%1}, [%2];" : "=r"(r.x), "=r"(r.y) : "r"(a) : "memory"); return r;
}
__device__ __forceinline__ uint4 lds128(uint32_t a) {
  uint4 r;
  asm volatile("ld.shared.v4.u32 {%0,%1,%2,%3}, [%4];" : "=r"(r.x), "=r"(r.y), "=r"(r.z), "=r"(r.w) : "r"(a) : "memory");
  return r;
}
__device__ __forceinline__ void sts32(uint32_t a, uint32_t v) { asm volatile("st.shared.u32 [%0], %1;" ::"r"(a), "r"(v) : "memory"); }
__device__ __forceinline__ void sts16(uint32_t a, uint32_t v) {
  asm volatile("{\n.reg .u16 h;\ncvt.u16.u32 h, %1;\nst.shared.u16 [%0], h;\n}\n" ::"r"(a), "r"(v) : "memory");
}
__device__ __forceinline__ void sts64(uint32_t a, uint32_t x, uint32_t y) {
  asm volatile("st.shared.v2.u32 [%0], {%1,%2};" ::"r"(a), "r"(x), "r"(y) : "memory");
}
__device__ __forceinline__ void sts128(uint32_t a, uint32_t x, uint32_t y, uint32_t z, uint32_t w) {
  asm volatile("st.shared.v4.u32 [%0], {%1,%2,%3,%4};" ::"r"(a), "r"(x), "r"(y), "r"(z), "r"(w) : "memory");
}
__device__ __forceinline__ uint4 ld_x(const uint4* p) {
  uint4 r;
  asm volatile("{\n.reg .b128 t;\nld.relaxed.gpu.global.b128 t, [%4];\nmov.b128 {%0,%1,%2,%3}, t;\n}\n"
               : "=r"(r.x), "=r"(r.y), "=r"(r.z), "=r"(r.w) : "l"(p) : "memory");
  return r;
}
__device__ __forceinline__ uint32_t ld_x32(const uint32_t* p) {
  uint32_t r; asm volatile("ld.relaxed.gpu.global.u32 %0, [%1];" : "=r"(r) : "l"(p) : "memory"); return r;
}
__device__ __forceinline__ void st_x(uint4* p, uint32_t x, uint32_t y, uint32_t z, uint32_t w) {
  asm volatile("{\n.reg .b128 t;\nmov.b128 t, {%1,%2,%3,%4};\nst.relaxed.gpu.global.b128 [%0], t;\n}\n"
               ::"l"(p), "r"(x), "r"(y), "r"(z), "r"(w) : "memory");
}
__device__ __forceinline__ void st_x_p(int p, uint4* a, uint32_t x, uint32_t y, uint32_t z, uint32_t w) {
  asm volatile("{\n.reg .b128 t;\n.reg .pred q;\nsetp.ne.b32 q, %5, 0;\nmov.b128 t, {%1,%2,%3,%4};\n@q st.relaxed.gpu.global.b128 [%0], t;\n}\n"
               ::"l"(a), "r"(x), "r"(y), "r"(z), "r"(w), "r"(p) : "memory");
}
__device__ __forceinline__ void sts64_p(int p, uint32_t a, uint32_t x, uint32_t y) {
  asm volatile("{\n.reg .pred q;\nsetp.ne.b32 q, %3, 0;\n@q st.shared.v2.u32 [%0], {%1,%2};\n}\n" ::"r"(a), "r"(x), "r"(y), "r"(p) : "memory");
}
__device__ __forceinline__ void st_x32(uint32_t* p, uint32_t x) {
  asm volatile("st.relaxed.gpu.global.u32 [%0], %1;" ::"l"(p), "r"(x) : "memory");
}
__device__ __forceinline__ uint32_t nz(uint32_t w) { return max(w, 1u); }
__device__ __forceinline__ uint32_t fu(float x) { return __float_as_uint(x); }
__device__ __forceinline__ float uf(uint32_t x) { return __uint_as_float(x); }

__device__ __forceinline__ void wgmma_ss_n96(float (&d)[48], uint64_t da, uint64_t db, int sc) {
  asm volatile("{\n.reg .pred p;\nsetp.ne.b32 p, %50, 0;\n"
      "wgmma.mma_async.sync.aligned.m64n96k16.f32.bf16.bf16 "
      "{%0,%1,%2,%3,%4,%5,%6,%7,%8,%9,%10,%11,%12,%13,%14,%15,%16,%17,%18,%19,%20,%21,%22,%23,%24,%25,%26,%27,%28,%29,%30,%31,%32,%33,%34,%35,%36,%37,%38,%39,%40,%41,%42,%43,%44,%45,%46,%47}, "
      "%48, %49, p, 1, 1, 0, 1;\n}\n"
      : "+f"(d[0]), "+f"(d[1]), "+f"(d[2]), "+f"(d[3]), "+f"(d[4]), "+f"(d[5]), "+f"(d[6]), "+f"(d[7]),
        "+f"(d[8]), "+f"(d[9]), "+f"(d[10]), "+f"(d[11]), "+f"(d[12]), "+f"(d[13]), "+f"(d[14]), "+f"(d[15]),
        "+f"(d[16]), "+f"(d[17]), "+f"(d[18]), "+f"(d[19]), "+f"(d[20]), "+f"(d[21]), "+f"(d[22]), "+f"(d[23]),
        "+f"(d[24]), "+f"(d[25]), "+f"(d[26]), "+f"(d[27]), "+f"(d[28]), "+f"(d[29]), "+f"(d[30]), "+f"(d[31]),
        "+f"(d[32]), "+f"(d[33]), "+f"(d[34]), "+f"(d[35]), "+f"(d[36]), "+f"(d[37]), "+f"(d[38]), "+f"(d[39]),
        "+f"(d[40]), "+f"(d[41]), "+f"(d[42]), "+f"(d[43]), "+f"(d[44]), "+f"(d[45]), "+f"(d[46]), "+f"(d[47])
      : "l"(da), "l"(db), "r"(sc));
}

__device__ __forceinline__ void wgmma_ss_n128(float (&d)[64], uint64_t da, uint64_t db, int sc) {
  asm volatile("{\n.reg .pred p;\nsetp.ne.b32 p, %66, 0;\n"
      "wgmma.mma_async.sync.aligned.m64n128k16.f32.bf16.bf16 "
      "{%0,%1,%2,%3,%4,%5,%6,%7,%8,%9,%10,%11,%12,%13,%14,%15,%16,%17,%18,%19,%20,%21,%22,%23,%24,%25,%26,%27,%28,%29,%30,%31,%32,%33,%34,%35,%36,%37,%38,%39,%40,%41,%42,%43,%44,%45,%46,%47,%48,%49,%50,%51,%52,%53,%54,%55,%56,%57,%58,%59,%60,%61,%62,%63}, "
      "%64, %65, p, 1, 1, 0, 1;\n}\n"
      : "+f"(d[0]), "+f"(d[1]), "+f"(d[2]), "+f"(d[3]), "+f"(d[4]), "+f"(d[5]), "+f"(d[6]), "+f"(d[7]),
        "+f"(d[8]), "+f"(d[9]), "+f"(d[10]), "+f"(d[11]), "+f"(d[12]), "+f"(d[13]), "+f"(d[14]), "+f"(d[15]),
        "+f"(d[16]), "+f"(d[17]), "+f"(d[18]), "+f"(d[19]), "+f"(d[20]), "+f"(d[21]), "+f"(d[22]), "+f"(d[23]),
        "+f"(d[24]), "+f"(d[25]), "+f"(d[26]), "+f"(d[27]), "+f"(d[28]), "+f"(d[29]), "+f"(d[30]), "+f"(d[31]),
        "+f"(d[32]), "+f"(d[33]), "+f"(d[34]), "+f"(d[35]), "+f"(d[36]), "+f"(d[37]), "+f"(d[38]), "+f"(d[39]),
        "+f"(d[40]), "+f"(d[41]), "+f"(d[42]), "+f"(d[43]), "+f"(d[44]), "+f"(d[45]), "+f"(d[46]), "+f"(d[47]),
        "+f"(d[48]), "+f"(d[49]), "+f"(d[50]), "+f"(d[51]), "+f"(d[52]), "+f"(d[53]), "+f"(d[54]), "+f"(d[55]),
        "+f"(d[56]), "+f"(d[57]), "+f"(d[58]), "+f"(d[59]), "+f"(d[60]), "+f"(d[61]), "+f"(d[62]), "+f"(d[63])
      : "l"(da), "l"(db), "r"(sc));
}

__device__ __forceinline__ void wgmma_rs_n16(float (&d)[8], const uint4& a, uint64_t db, int sc) {
  asm volatile("{\n.reg .pred p;\nsetp.ne.b32 p, %13, 0;\n"
      "wgmma.mma_async.sync.aligned.m64n16k16.f32.bf16.bf16 "
      "{%0,%1,%2,%3,%4,%5,%6,%7}, "
      "{%8,%9,%10,%11}, %12, p, 1, 1, 1;\n}\n"
      : "+f"(d[0]), "+f"(d[1]), "+f"(d[2]), "+f"(d[3]), "+f"(d[4]), "+f"(d[5]), "+f"(d[6]), "+f"(d[7])
      : "r"(a.x), "r"(a.y), "r"(a.z), "r"(a.w), "l"(db), "r"(sc));
}

struct Params {
  const __nv_bfloat16 *logA, *Aim, *Cre, *Cim, *logdt, *Dskip, *x, *wphi, *wo;
  __nv_bfloat16* out;
  uint4* xs;
  long long* ts;
};

__device__ __forceinline__ uint4 tr_row(const uint4 (&v)[8], int i) {
  uint32_t o[4];
#pragma unroll
  for (int m = 0; m < 4; m++) {
    const uint4 &ra = v[2 * m], &rb = v[2 * m + 1];
    const int k = i >> 1;
    const uint32_t xa = k == 0 ? ra.x : k == 1 ? ra.y : k == 2 ? ra.z : ra.w;
    const uint32_t xb = k == 0 ? rb.x : k == 1 ? rb.y : k == 2 ? rb.z : rb.w;
    o[m] = __byte_perm(xa, xb, (i & 1) ? 0x7632 : 0x5410);
  }
  return make_uint4(o[0], o[1], o[2], o[3]);
}

struct cpx { float r, i; };
__device__ __forceinline__ cpx cmul(cpx a, cpx b) { return {a.r * b.r - a.i * b.i, a.r * b.i + a.i * b.r}; }
__device__ __forceinline__ cpx csq(cpx a) { return {a.r * a.r - a.i * a.i, 2.f * (a.r * a.i)}; }
__device__ __forceinline__ cpx polar(float e, float t) {
  const float m = ex2(e);
  return {m * __cosf(t), m * __sinf(t)};
}

struct KgenRaw { unsigned short la, ai, cr, ci, ldt; };
__device__ __forceinline__ KgenRaw kgen_load(const Params& P, int d, int unit, int lane) {
  const int o = d * 128 + unit * 32 + lane;
  return {__ldg((const unsigned short*)P.logA + o), __ldg((const unsigned short*)P.Aim + o), __ldg((const unsigned short*)P.Cre + o),
          __ldg((const unsigned short*)P.Cim + o), __ldg((const unsigned short*)P.logdt + d)};
}
__device__ __forceinline__ void kgen_unit(const KgenRaw& r, int lane, uint32_t buf, uint32_t open_bar, float& dt,
                                          float (&k)[5][4], float& k2048) {
  dt = bf_round(expf(bf_lo(r.ldt)));
  const float a2 = -(bf_round(expf(bf_lo(r.la))) * dt) * 1.4426950408889634f;
  const float f = bf_lo(r.ai) * dt;
  const float r128 = f * 20.371832715762604f;
  const cpx C = {bf_lo(r.cr), -bf_lo(r.ci)};
  const uint32_t sa = buf + (lane & 7) * 128 + ((((lane >> 3) ^ lane) & 7) << 4);
  const uint32_t lb = buf + (lane >> 3) * 128 + (((lane ^ (lane >> 3)) & 7) << 4);
  const uint32_t la = buf + ((lane >> 3) & 1) * 1024 + (lane >> 4) * 128 + (((lane ^ (lane >> 4)) & 7) << 4);
  auto put = [&](const cpx (&v)[8], uint32_t off) {
    stsm4(sa + off, pack_bf(v[0].r, v[0].i), pack_bf(v[1].r, v[1].i), pack_bf(v[2].r, v[2].i), pack_bf(v[3].r, v[3].i));
    stsm4((sa ^ 64) + off, pack_bf(v[4].r, v[4].i), pack_bf(v[5].r, v[5].i), pack_bf(v[6].r, v[6].i), pack_bf(v[7].r, v[7].i));
  };
  uint32_t A[4][4], B[5][2][4];
  auto getB = [&](int j, uint32_t off) {
    __syncwarp();
    ldsm4(B[j][0], lb + off);
    ldsm4(B[j][1], (lb ^ 64) + 512 + off);
  };
  cpx t0[8], t1[8], t2[8], t3[8], t4[8];
  t0[0] = {1.f, 0.f};
  t0[1] = polar(a2, f);
  t1[0] = polar(a2 * 128.f, (r128 - rintf(r128)) * 6.283185307179586f);
  t0[2] = csq(t0[1]); t0[4] = csq(t0[2]);
  t2[0] = csq(t1[0]); t3[0] = csq(t2[0]); t4[0] = csq(t3[0]);
  t0[3] = cmul(t0[2], t0[1]); t0[5] = cmul(t0[4], t0[1]); t0[6] = cmul(t0[4], t0[2]); t0[7] = cmul(t0[4], t0[3]);
  put(t0, 0); getB(0, 0);
  {
    cpx w8 = csq(t0[4]);
    w8.i = -w8.i;
    const cpx w16 = csq(w8), w32 = csq(w16), w64 = csq(w32);
    cpx a[8];
    a[0] = C; a[1] = cmul(C, w8);
    a[2] = cmul(a[0], w16); a[3] = cmul(a[1], w16);
#pragma unroll
    for (int i = 0; i < 4; i++) a[4 + i] = cmul(a[i], w32);
    put(a, 0);
#pragma unroll
    for (int i = 0; i < 8; i++) a[i] = cmul(a[i], w64);
    put(a, 1024);
    __syncwarp();
#pragma unroll
    for (int s = 0; s < 4; s++) ldsm4(A[s], (la ^ (s << 5)) + s * 256);
  }
#pragma unroll
  for (int i = 1; i < 8; i++) t1[i] = cmul(t0[i], t1[0]);
  put(t1, 0); getB(1, 0);
#pragma unroll
  for (int i = 1; i < 8; i++) t2[i] = cmul((i & 1) ? t1[i & 6] : t0[i & 6], t2[0]);
  put(t2, 1024); getB(2, 1024);
#pragma unroll
  for (int i = 1; i < 8; i++) t3[i] = cmul((i & 2) ? t2[i & 5] : ((i & 1) ? t1[i & 4] : t0[i & 4]), t3[0]);
  put(t3, 0); getB(3, 0);
#pragma unroll
  for (int i = 1; i < 8; i++) t4[i] = cmul((i & 4) ? t3[i & 3] : ((i & 2) ? t2[i & 1] : t1[0]), t4[0]);
  put(t4, 1024); getB(4, 1024);
  const cpx we = csq(t4[0]);
  k2048 += C.r * we.r + C.i * we.i;
  if (open_bar) {
    if (lane == 0 && (B[4][0][0] & B[4][1][0]) != 0xffffffffu) mbar_arrive(BAR(MB_AUX));
    mbar_wait(open_bar);
  }
#pragma unroll
  for (int s = 0; s < 4; s++)
#pragma unroll
    for (int j = 0; j < 5; j++)
      mma(k[j][0], k[j][1], k[j][2], k[j][3], A[s][0], A[s][1], A[s][2], A[s][3], B[j][s >> 1][2 * (s & 1)], B[j][s >> 1][2 * (s & 1) + 1]);
}

__device__ __forceinline__ void build_tables(uint32_t tb, int lane, float (&k)[5][4], float k2048) {
  const int g = lane >> 2, c = lane & 3;
  const uint32_t kc = tb + T_KC + 16;
  {
    const uint32_t a0 = kc + 16 * g + 4 * c, a2 = kc + 2 * (256 + 4 * g + c);
    const uint32_t a3 = kc + 2 * (384 + 2 * g + 64 * (c & 1) + (c >> 1)), a4 = kc + 2 * (512 + g + 32 * c);
#pragma unroll
    for (int r = 0; r < 2; r++) {
      sts32(a0 + 128 * r, pack_bf(k[0][2 * r], k[0][2 * r + 1]));
      sts32(a0 + 128 * r + 256, pack_bf(k[1][2 * r], k[1][2 * r + 1]));
      const uint32_t w2 = pack_bf(k[2][2 * r], k[2][2 * r + 1]);
      const uint32_t w3 = pack_bf(k[3][2 * r], k[3][2 * r + 1]);
      const uint32_t w4 = pack_bf(k[4][2 * r], k[4][2 * r + 1]);
      sts16(a2 + 64 * r, w2); sts16(a2 + 64 * r + 128, w2 >> 16);
      sts16(a3 + 32 * r, w3); sts16(a3 + 32 * r + 64, w3 >> 16);
      sts16(a4 + 16 * r, w4); sts16(a4 + 16 * r + 32, w4 >> 16);
    }
  }
  if (lane == 0) { sts16(kc + 2 * 640, pack_bf(k2048, 0.f)); sts16(kc - 2, 0); }
  __syncwarp();
  const uint32_t td = tb + T_D + 32;
  {
    const uint4 v = lds128(kc + 16 * lane);
    const uint32_t pv = lds16(kc + 16 * lane - 2);
    sts128(td + 32 * lane, __byte_perm(v.x, pv, 0x5410), __byte_perm(v.x, v.x, 0x1032), __byte_perm(v.y, v.x, 0x7610),
           __byte_perm(v.y, v.y, 0x1032));
    sts128(td + 32 * lane + 16, __byte_perm(v.z, v.y, 0x7610), __byte_perm(v.z, v.z, 0x1032),
           __byte_perm(v.w, v.z, 0x7610), __byte_perm(v.w, v.w, 0x1032));
  }
  {
    const uint2 v = lds64(kc + 512 + 8 * lane);
    const uint32_t k4 = lds16(kc + 512 + 8 * lane + 8);
    const uint32_t pv = lds16(kc + (lane == 0 ? 510 : 512 + 8 * lane));
    const uint32_t k22 = __byte_perm(v.y, v.y, 0x1010);
    sts128(td + 1024 + 32 * lane, __byte_perm(v.x, pv, 0x5410), __byte_perm(v.x, v.x, 0x1010),
           __byte_perm(v.x, v.x, 0x1032), __byte_perm(v.y, v.x, 0x7610));
    sts128(td + 1024 + 32 * lane + 16, k22, k22, __byte_perm(v.y, v.y, 0x1032), __byte_perm(k4, v.y, 0x7610));
  }
  {
    const uint32_t kk = lds16(kc + 2 * 384);
    const uint32_t w = lane < 3 ? (kk | (kk << 16)) : (lane == 3 ? (kk << 16) : 0u);
    if (lane < 24) sts32(td + 4 * (lane < 16 ? 512 + lane : lane - 24), w);
    const uint32_t lo_ = lds16(kc + 2 * 511), le_ = lds16(kc + 2 * 512);
    const uint32_t ja = tb + T_5 + (lane < 16 ? 4 * lane : 256 + 4 * lane);
    sts32(ja, lane == 16 ? (le_ << 16) : 0u);
    sts32(ja + 384, lane == 16 ? (lo_ << 16) : 0u);
    sts32(tb + (lane < 16 ? T_7 : T_9 - 64) + 4 * lane, 0u);
  }
#pragma unroll
  for (int s = 0; s < 2; s++) {
    const uint32_t b = kc + 2 * (s ? 512 : 384) + 8 * lane;
    const uint2 v = lds64(b);
    uint32_t em = lds16(b - 2), e0 = v.x;
    const uint32_t e4 = lds16(b + 8);
    if (lane == 0) { em = 0; e0 = 0; }
    sts64(tb + (s ? T_7 : T_3) + 64 + 8 * lane, __byte_perm(v.x, em, 0x5432), __byte_perm(v.y, v.x, 0x7632));
    sts64(tb + (s ? T_9 : T_5) + 64 + 8 * lane, __byte_perm(v.y, e0, 0x5410), __byte_perm(e4, v.y, 0x5410));
  }
  __syncwarp();
}

__device__ __forceinline__ uint32_t box2w(int lo, int n, int o) {
  return ((unsigned)(o - lo) < (unsigned)n ? 0x3F80u : 0u) | ((unsigned)(o + 1 - lo) < (unsigned)n ? 0x3F800000u : 0u);
}

__device__ __forceinline__ void conv_channel(uint32_t ub, uint32_t tb, int lane, uint4* ydst) {
  const int g = lane >> 2, c = lane & 3, x = g - 2 * c;
  const uint32_t st = tb + T_ST + lane * 8;
  const int mi = lane >> 3;
  const uint32_t qa = ub + U_PAD + 16 * (lane & 7) + ((mi == 0 || mi == 3) ? U_ODD : 0) - (mi == 0 ? 16 : 0);
  const uint32_t kv = lds16(tb + T_KC + 16 + 2 * 512);
  {
    const uint32_t hb = ub + U_PAD + (mi & 1) * U_ODD + 16 * ((lane >> 4) + (lane & 7)) - 16;
    const int oh = c < 2 ? 8 + 2 * c : 2 * c - 8;
    const uint32_t bx0 = box2w(g - 4, 9, 2 * c), bx1 = box2w(g - 3, 7, 2 * c), bx2 = box2w(g - 4, 9, oh), bx3 = box2w(g - 3, 7, oh);
    uint32_t f7[9], f9a[9], f9b[9];
    const uint32_t fa = tb + T_7 + 4 * (8 + x);
#pragma unroll
    for (int m = 0; m < 9; m++) {
      f7[m] = lds32(fa + 32 * m);
      f9b[m] = lds32(fa + 320 + 32 * m);
      f9a[m] = lds32(fa + 316 + 32 * m);
    }
    TS(36);
    uint32_t z09[8], z07[8], zm9[8], zm7[8];
#pragma unroll
    for (int i = 0; i < 8; i++) {
      uint32_t h[4];
      ldsm4(h, hb + 128 * i);
      float y0, y1, y2, y3, w0, w1, w2, w3;
      mma0(y0, y1, y2, y3, bx0, bx1, bx2, bx3, h[2], c < 2 ? h[3] : h[1]);
      mma0(w0, w1, w2, w3, bx0, bx1, bx2, bx3, h[1], c < 2 ? h[2] : h[0]);
      z09[i] = pack_bf(y0, y1); z07[i] = pack_bf(y2, y3);
      zm9[i] = pack_bf(w0, w1); zm7[i] = pack_bf(w2, w3);
    }
    float a[4][2][4];
#pragma unroll
    for (int kap = 0; kap < 4; kap++)
#pragma unroll
      for (int sg = 0; sg < 2; sg++)
#pragma unroll
        for (int bk = 3; bk >= kap; bk--) {
          const int m = 2 * (bk - kap) + 1;
          float(&a0)[4] = a[bk][0];
          float(&a1)[4] = a[bk][1];
          if (sg == 0 && kap == 0) {
            mma0(a0[0], a0[1], a0[2], a0[3], f9a[m], f9a[m + 1], f9a[m - 1], f9a[m], z09[0], z09[1]);
            mma0(a1[0], a1[1], a1[2], a1[3], f9b[m], f9b[m + 1], f9b[m - 1], f9b[m], zm9[0], zm9[1]);
          } else if (sg == 0) {
            mma(a0[0], a0[1], a0[2], a0[3], f9a[m], f9a[m + 1], f9a[m - 1], f9a[m], z09[2 * kap], z09[2 * kap + 1]);
            mma(a1[0], a1[1], a1[2], a1[3], f9b[m], f9b[m + 1], f9b[m - 1], f9b[m], zm9[2 * kap], zm9[2 * kap + 1]);
          } else {
            mma(a0[0], a0[1], a0[2], a0[3], f7[m], f7[m + 1], f7[m - 1], f7[m], zm7[2 * kap], zm7[2 * kap + 1]);
            mma(a1[0], a1[1], a1[2], a1[3], f7[m], f7[m + 1], f7[m - 1], f7[m], z07[2 * kap], z07[2 * kap + 1]);
          }
        }
#pragma unroll
    for (int bk = 0; bk < 4; bk++) {
      sts64(st + 256 * (8 + 2 * bk), pack_bf(a[bk][0][0], a[bk][0][1]), pack_bf(a[bk][1][0], a[bk][1][1]));
      sts64(st + 256 * (9 + 2 * bk), pack_bf(a[bk][0][2], a[bk][0][3]), pack_bf(a[bk][1][2], a[bk][1][3]));
    }
  }
  TS(44);
  {
    const int oh = c < 3 ? 2 * c : -10;
    const uint32_t bx0 = box2w(g - 10, 5, 2 * c - 8), bx1 = box2w(g - 5, 3, 2 * c - 8), bx2 = box2w(g - 10, 5, oh), bx3 = box2w(g - 5, 3, oh);
    const uint32_t lb0 = ((unsigned)(x + 5) < 2u ? kv : 0u) | ((unsigned)(x + 4) < 2u ? kv << 16 : 0u);
    const uint32_t lb1 = ((unsigned)(x - 3) < 2u ? kv : 0u) | ((unsigned)(x - 4) < 2u ? kv << 16 : 0u);
    const int q0 = g - 1, q1 = c < 3 ? g : g - 2;
    uint32_t y0a = ub + U_PAD + (q0 & 1) * U_ODD + 16 * (q0 >> 1) + 4 * c;
    uint32_t y1a = ub + U_PAD + (q1 & 1) * U_ODD + 16 * (q1 >> 1) + 4 * c;
    uint2 a5[10], a3[10];
    const uint32_t aa = tb + T_5 + 4 * (8 + 2 * g - 2 * c);
#pragma unroll
    for (int m = 0; m < 10; m++) { a5[m] = lds64(aa + 32 * m); a3[m] = lds64(aa + 384 + 32 * m); }
    float T[6][4];
#pragma unroll
    for (int i = 0; i < 6; i++) T[i][0] = T[i][1] = T[i][2] = T[i][3] = 0.f;
    uint32_t x5[2] = {0, 0}, x3[2] = {0, 0}, yb[4], lq[4];
    uint32_t lqa = qa, sta = st + 256 * 8;
    uint2 sv;
    auto fetch = [&]() {
      yb[0] = lds32(y0a); yb[1] = lds32(y1a); yb[2] = lds32(y0a + 64); yb[3] = lds32(y1a + 64);
      ldsm4(lq, lqa);
      sv = lds64(min(sta, st + 256 * 15));
      y0a += 128; y1a += 128; lqa += 128; sta += 256;
    };
    fetch();
#pragma unroll 2
    for (int kap = -1; kap < 13; kap++) {
      float yn[2][4];
      mma0(yn[0][0], yn[0][1], yn[0][2], yn[0][3], bx0, bx1, bx2, bx3, yb[0], yb[1]);
      mma0(yn[1][0], yn[1][1], yn[1][2], yn[1][3], bx0, bx1, bx2, bx3, yb[2], yb[3]);
      sts64_p(kap > 0, sta - 256 * 7, pack_bf(T[0][0], T[0][1]), pack_bf(T[0][2], T[0][3]));
#pragma unroll
      for (int i = 0; i < 5; i++)
        mmac_p((unsigned)kap < 12u - i, T[i], a5[2 * i + 1].x, a5[2 * i + 1].y, a5[2 * i].x, a5[2 * i].y, x5[0], x5[1], T[i + 1]);
      const float ci[4] = {bf_lo(sv.x), bf_hi(sv.x), bf_lo(sv.y), bf_hi(sv.y)};
      mmac_p(kap < 7, T[5], lq[0], lq[1], lq[2], lq[3], lb0, lb1, ci);
      fetch();
#pragma unroll
      for (int i = 0; i < 5; i++)
        mma_p((unsigned)kap < 12u - i, T[i], a3[2 * i + 1].x, a3[2 * i + 1].y, a3[2 * i].x, a3[2 * i].y, x3[0], x3[1]);
#pragma unroll
      for (int hh = 0; hh < 2; hh++) { x5[hh] = pack_bf(yn[hh][0], yn[hh][1]); x3[hh] = pack_bf(yn[hh][2], yn[hh][3]); }
    }
  }
  TS(45);
  {
    uint32_t F[66];
    const uint32_t fa = tb + T_D + 32 + 4 * x;
#pragma unroll
    for (int m = 0; m < 66; m++) F[m] = lds32(fa + 32 * m);
    float T[5][4];
#pragma unroll
    for (int i = 0; i < 5; i++) T[i][0] = T[i][1] = T[i][2] = T[i][3] = 0.f;
    uint32_t qd[8][4], held[2] = {0, 0};
    uint32_t qp = qa + 128 * 15, sta = st + 256 * 14;
    uint4* yd = ydst + 19 * 16;
#pragma unroll
    for (int i = 0; i < 6; i++) ldsm4(qd[i], qp - 16 * i);
    uint2 sv = lds64(sta + 256);
    float ci[4] = {bf_lo(sv.x), bf_hi(sv.x), bf_lo(sv.y), bf_hi(sv.y)};
    TS(46);
#pragma unroll 2
    for (int be = 15; be >= 0; be--) {
#pragma unroll
      for (int k = 4; k >= 1; k--)
        mmac_p(be <= 15 - k, T[k], qd[0][0], qd[0][1], qd[0][2], qd[0][3], F[16 * k + 1], F[16 * k], T[k - 1]);
      mmac(T[0], qd[0][0], qd[0][1], qd[0][2], qd[0][3], F[1], F[0], ci);
      ldsm4(qd[6], qp - 16 * 6);
      ldsm4(qd[7], qp - 16 * 7);
      sv = lds64(sta);
#pragma unroll
      for (int i = 1; i < 8; i++) {
#pragma unroll
        for (int k = 3; k >= 0; k--)
          mma_p(k == 0 || be <= 15 - k, T[k], qd[i][0], qd[i][1], qd[i][2], qd[i][3], F[16 * k + 2 * i + 1], F[16 * k + 2 * i]);
        if (i < 7) ldsm4(qd[i - 1], qp - 128 - 16 * (i - 1));
        if (i == 2) {
          const uint32_t w0 = pack_bf(T[4][0], T[4][1]), w1 = pack_bf(T[4][2], T[4][3]);
          st_x_p(be <= 10 && !(be & 1), yd, nz(w0), w1, held[0], held[1]);
          held[0] = w0; held[1] = w1;
        }
        if (i == 4) {
          if (be <= 4) sv = make_uint2(0, 0);
          ci[0] = bf_lo(sv.x); ci[1] = bf_hi(sv.x); ci[2] = bf_lo(sv.y); ci[3] = bf_hi(sv.y);
        }
      }
      qp -= 128; sta -= 256; yd -= 16;
    }
#pragma unroll
    for (int B = 1; B >= 0; B--)
      st_x(ydst + B * 32, nz(pack_bf(T[2 * B][0], T[2 * B][1])), pack_bf(T[2 * B][2], T[2 * B][3]),
           pack_bf(T[2 * B + 1][0], T[2 * B + 1][1]), pack_bf(T[2 * B + 1][2], T[2 * B + 1][3]));
  }
}

__device__ __forceinline__ void dual_exp(const uint32_t* w, uint32_t* e) {
  const float L = 1.44268798828125f;
  uint32_t mx = bmax2(bmax2(w[0], w[1]), bmax2(w[2], w[3]));
  uint32_t mn = bmin2(bmin2(w[0], w[1]), bmin2(w[2], w[3]));
  mx = bmax2(mx, __shfl_xor_sync(0xffffffffu, mx, 1));
  mn = bmin2(mn, __shfl_xor_sync(0xffffffffu, mn, 1));
  mx = bmax2(mx, __shfl_xor_sync(0xffffffffu, mx, 2));
  mn = bmin2(mn, __shfl_xor_sync(0xffffffffu, mn, 2));
  const float mx0 = bf_lo(mx) * -L, mx1 = bf_hi(mx) * -L, mn0 = bf_lo(mn) * L, mn1 = bf_hi(mn) * L;
#pragma unroll
  for (int i = 0; i < 2; i++) {
    const float a0 = bf_lo(w[2 * i]), a1 = bf_hi(w[2 * i]), b0 = bf_lo(w[2 * i + 1]), b1 = bf_hi(w[2 * i + 1]);
    e[2 * i] = pack_bf(ex2(fmaf(a0, L, mx0)), ex2(fmaf(b0, L, mx0)));
    e[2 * i + 1] = pack_bf(ex2(fmaf(a1, L, mx1)), ex2(fmaf(b1, L, mx1)));
    e[4 + 2 * i] = pack_bf(ex2(fmaf(a0, -L, mn0)), ex2(fmaf(b0, -L, mn0)));
    e[5 + 2 * i] = pack_bf(ex2(fmaf(a1, -L, mn1)), ex2(fmaf(b1, -L, mn1)));
  }
}
__device__ __forceinline__ void norm_store(const uint32_t* e, uint32_t dst) {
  float s[4];
  mma0(s[0], s[1], s[2], s[3], e[0], e[1], e[2], e[3], 0x3F803F80u, 0x3F803F80u);
  const uint32_t r = pack_bf(rcp(s[0]), rcp(s[2]));
  const __nv_bfloat162 rr = *(const __nv_bfloat162*)&r;
  uint32_t o[4];
#pragma unroll
  for (int i = 0; i < 4; i++) {
    const __nv_bfloat162 v = __hmul2(*(const __nv_bfloat162*)&e[i], (i & 1) ? __high2bfloat162(rr) : __low2bfloat162(rr));
    o[i] = *(const uint32_t*)&v;
  }
  stsm4(dst, o[0], o[1], o[2], o[3]);
}

__global__ void __launch_bounds__(NTHREADS, 1)
fused_kernel(const Params P, const __grid_constant__ CUtensorMap mx, const __grid_constant__ CUtensorMap mw,
             const __grid_constant__ CUtensorMap mo, const __grid_constant__ CUtensorMap mu,
             const __grid_constant__ CUtensorMap mout) {
  constexpr uint32_t sb = SB;
  const int tid = threadIdx.x, lane = tid & 31;
  const int warp = __shfl_sync(0xffffffffu, tid >> 5, 0);
  const int b = blockIdx.x, oct = b >> 3, i8 = b & 7;
  const int rt = oct < 8 ? oct : 15 - oct;
  const int hp = (oct >> 3) * 8 + i8;

  const int d = b * 4 + ((tid >> 5) & 3);
  KgenRaw raw = {}, raw3 = {};
  unsigned short dsk = 0;
  if (tid < 384) {
    asm volatile("prefetch.tensormap [%0];" ::"l"(&mu) : "memory");
    asm volatile("prefetch.tensormap [%0];" ::"l"(&mw) : "memory");
    asm volatile("prefetch.tensormap [%0];" ::"l"(&mx) : "memory");
    raw = kgen_load(P, d, tid >> 7, lane);
    raw3 = kgen_load(P, d, 3, lane);
    dsk = __ldg((const unsigned short*)P.Dskip + d);
  }
  if (warp >= 12) asm volatile("setmaxnreg.dec.sync.aligned.u32 32;");
  if (warp == 12) {
    if (lane == 0) {
#pragma unroll
      for (int i = 0; i < 9; i++) mbar_init(BAR(i), 1);
      asm volatile("fence.mbarrier_init.release.cluster;" ::: "memory");
    }
    __syncwarp();
    if (lane < 9) mbar_expect(BAR(0) + 8 * lane, lane == 0 ? 16384 : 28672);
    __syncwarp();
    nb_arrive(NB_PREP, 448);
#pragma unroll 1
    for (int kb = 0; kb < 8; kb++) {
      if (kb == STEP_U) e_tma5d(sb + OFF_STG0, &mu, BAR(MB_URAW), i8 * 64, oct * 4);
      e_tma3d(sb + OFF_W + kb * 12288, &mw, BAR(MB_FULL) + 8 * kb, hp * 32, kb * 64, 0);
      if (kb < 5) e_tma2d(sb + OFF_X + (kb < 2 ? kb + 3 : kb - 2) * 16384, &mx, BAR(MB_FULL) + 8 * kb, kb * 64, rt * 256);
    }
    if (smem_u32(smem_raw) != SB) __trap();
  }
  if (warp >= 12) {
    if (warp == 12) {
      nb_sync(NB_PROD, 64);
      e_prefetch(P.x + (size_t)(rt * 256 + hp * 16) * 512, 16384);
      uint32_t slot = sb + OFF_X + 3 * 16384;
#pragma unroll 1
      for (int n = 0; n < 11; n++) {
        mbar_wait(BAR(MB_EMPTY) + 8 * n);
        const int m = n + 5;
        e_tma2d(slot, &mx, BAR(MB_FULL) + 8 * m, (m & 7) * 64, rt * 256 + (m >> 3) * 128);
        slot = slot == sb + OFF_X + 4 * 16384 ? sb + OFF_X : slot + 16384;
        if (n == 7) e_prefetch(P.wo + (size_t)b * 2048, 4096);
      }
#pragma unroll 1
      for (int i = 0; i < 8; i++) {
        mbar_wait(BAR(MB_EMPTY + 10) + 8 * ((0x54332100u >> (4 * i)) & 7));
        const int w0 = (0x54736210u >> (4 * i)) & 7;
        e_tma3d(sb + OFF_W + w0 * 16384, &mo, BAR(MB_WO), 0, w0 * 64, (hp & 3) * 2);
      }
    } else {
      if (warp == 13) {
        if (lane == 0) {
#pragma unroll
          for (int i = 9; i < 39; i++) mbar_init(BAR(i), i < MB_EMPTY ? 1 : (i < MB_AUX ? 4 : 9));
          asm volatile("fence.mbarrier_init.release.cluster;" ::: "memory");
        }
        __syncwarp();
        if (lane < 9) mbar_expect(BAR(MB_FULL + 8) + 8 * lane, lane < 8 ? 16384 : 131072);
        __syncwarp();
        nb_arrive(NB_PROD, 64);
        nb_arrive(NB_PREP, 448);
      }
      nb_sync(NB_ZERO, 96);
      if (warp == 15) {
        const uint4 v0 = __ldg((const uint4*)P.wphi + hp * 64 + lane), v1 = __ldg((const uint4*)P.wphi + hp * 64 + 32 + lane);
        sts128(sb + OFF_PHI + (lane & 1) * 256 + (lane >> 1) * 16, v0.x, v0.y, v0.z, v0.w);
        sts128(sb + OFF_PHI + 512 + (lane & 1) * 256 + (lane >> 1) * 16, v1.x, v1.y, v1.z, v1.w);
        asm volatile("fence.proxy.async.shared::cta;" ::: "memory");
        __syncwarp();
        if (lane == 0) mbar_arrive(BAR(MB_AUX));
        mbar_wait(BAR(MB_EMPTY + ZERO_STEP));
        uint4* py = P.xs + X_Y + b * 1024 + lane;
#pragma unroll 1
        for (int i = 0; i < 1024; i += 32) st_x(py + i, 0, 0, 0, 0);
        nb_arrive(NB_YZ, 160);
        nb_arrive(NB_ODONE, 320);
        if (lane == 0) TS1(55);
        return;
      }
      uint32_t* const cnt = (uint32_t*)(P.xs + X_CNT) + (warp == 13 ? i8 : 8 + rt) * 32;
      const unsigned target = (ld_x32(cnt) & ~15u) + 16;
      if (warp == 13) {
        uint4* pp = P.xs + X_PART + (hp * 8 + rt) * 144 + lane;
#pragma unroll 1
        for (int i = 0; i < 144; i += 32) if (i + lane < 144) st_x(pp + i, 0, 0, 0, 0);
      }
      nb_sync(warp == 13 ? NB_INIT : NB_ODONE, warp == 13 ? 160 : 320);
      if (lane == 0) TS1(warp == 13 ? 49 : 56);
      asm volatile("fence.proxy.async.shared::cta;" ::: "memory");
      if (lane == 0) asm volatile("red.release.gpu.global.add.u32 [%0], 1;" ::"l"(cnt) : "memory");
      if (lane == 0) TS1(warp == 13 ? 50 : 57);
      const uint32_t* pc = (warp == 13 && (lane & 1)) ? (uint32_t*)(P.xs + X_CNT) + (b >> 4) * 32 : cnt;
#pragma unroll 1
      for (int i = 0; i < SPIN_MAX; i++) {
        unsigned v;
        asm volatile("ld.acquire.gpu.global.u32 %0, [%1];" : "=r"(v) : "l"(pc) : "memory");
        if (__all_sync(0xffffffffu, (int)(v - target) >= 0)) break;
      }
      if (lane == 0) TS1(warp == 13 ? 51 : 58);
      asm volatile("fence.proxy.async.global;" ::: "memory");
      if (warp == 13) {
        mbar_wait(BAR(MB_EMPTY + 11));
        e_expect(BAR(MB_UFULL), 4 * U_CH);
        e_bulk(sb + OFF_U, P.xs + X_UT + b * (U_CH / 4), 4 * U_CH, BAR(MB_UFULL));
      } else {
        const uint4* src = P.xs + X_O + (rt * 4 + (hp >> 2)) * 4096;
        e_expect(BAR(MB_OA), 14336);
        e_bulk(sb + OFF_STG0, src + 3200, 14336, BAR(MB_OA));
        e_expect(BAR(MB_OC), 32768);
        e_bulk(sb + OFF_X + 32768, src, 32768, BAR(MB_OC));
        nb_sync(NB_BDONE, 288);
        asm volatile("fence.proxy.async.shared::cta;" ::: "memory");
        e_expect(BAR(MB_OB), 18432);
        e_bulk(sb + OFF_U, src + 2048, 18432, BAR(MB_OB));
      }
    }
    return;
  }

  asm volatile("setmaxnreg.inc.sync.aligned.u32 160;");
  const int wg = warp >> 2, w = warp & 3, t = tid & 127;
  const int g = lane >> 2, c = lane & 3;
  const uint32_t tb = sb + OFF_T + w * T_CH;
  {
    float k[5][4], k2048 = 0.f, dt;
#pragma unroll
    for (int j = 0; j < 5; j++) k[j][0] = k[j][1] = k[j][2] = k[j][3] = 0.f;
    const uint32_t kp = tb + (wg & 1) * 2608;
#pragma unroll 1
    for (int r = 0; r <= (wg >> 1); r++) {
      kgen_unit(raw, lane, wg == 2 ? sb + OFF_STG0 + 16384 + w * 2048 : (kp + 127) & ~127u, r ? BAR(MB_EMPTY + 15) : 0u, dt, k, k2048);
      raw = raw3;
      TS(40 + wg + r);
      if (r == 0) {
        if (wg != 2) {
#pragma unroll
          for (int j = 0; j < 5; j++) sts128(kp + j * 512 + lane * 16, fu(k[j][0]), fu(k[j][1]), fu(k[j][2]), fu(k[j][3]));
          k2048 += __shfl_xor_sync(0xffffffffu, k2048, 16);
          k2048 += __shfl_xor_sync(0xffffffffu, k2048, 8);
          if (lane < 8) sts32(kp + 2560 + lane * 4, fu(k2048));
        } else if ((fu(k[0][0]) & fu(k[1][0]) & fu(k[2][0]) & fu(k[3][0]) & fu(k[4][0])) == 0xffffffffu) {
          sts32(kp, 0);
        }
        nb_sync(NB_PREP, 448);
        if (wg == 2) {
#pragma unroll 1
          for (int q = 0; q < 2; q++) {
            const uint32_t src = tb + q * 2608;
#pragma unroll
            for (int j = 0; j < 5; j++) {
              const uint4 v = lds128(src + j * 512 + lane * 16);
              k[j][0] += uf(v.x); k[j][1] += uf(v.y); k[j][2] += uf(v.z); k[j][3] += uf(v.w);
            }
            if (lane < 8) k2048 += uf(lds32(src + 2560 + lane * 4));
          }
        }
      }
    }
    if (wg == 2) {
      TS(34);
#pragma unroll
      for (int o2 = 16; o2; o2 >>= 1) k2048 += __shfl_xor_sync(0xffffffffu, k2048, o2);
      const float sc = 2.f * dt;
#pragma unroll
      for (int j = 0; j < 5; j++) { k[j][0] *= sc; k[j][1] *= sc; k[j][2] *= sc; k[j][3] *= sc; }
      k2048 *= sc;
      if (lane == 0) k[0][0] += bf_lo(dsk);
      build_tables(tb, lane, k, k2048);
      TS(35);
      nb_sync(NB_YZ, 160);
      mbar_wait(BAR(MB_UFULL));
      uint4* const g_y = P.xs + X_Y;
      conv_channel(sb + OFF_U + w * U_CH, tb, lane, g_y + (size_t)d * 256 + lane);
      nb_arrive(NB_BDONE, 288);
      TS(37);
      mbar_wait(BAR(MB_OA));
      const int lam = w * 8 + g;
      const uint4* src = g_y + (size_t)(oct * 32 + c * 8) * 256 + i8 * 32 + lam;
      uint4 v[8];
#pragma unroll 1
      for (int it = 0; it < SPIN_MAX; it++) {
        uint32_t m = 0xffffffffu;
#pragma unroll
        for (int i = 0; i < 8; i++) v[i] = ld_x(src + i * 256);
#pragma unroll
        for (int i = 0; i < 8; i++) m = min(m, v[i].x);
        if (__all_sync(0xffffffffu, m != 0)) break;
      }
      __nv_bfloat16* dst = P.out + (size_t)(i8 * 256 + (lam >> 2) * 16 + (lam & 3) * 2) * 1024 + 512 + oct * 32 + c * 8;
#pragma unroll
      for (int i = 0; i < 8; i++) *(uint4*)(dst + (size_t)((i >> 2) * 128 + ((i >> 1) & 1) * 8 + (i & 1)) * 1024) = tr_row(v, i);
      TS(38);
      GT(63);
      return;
    }
    if (wg == 1) {
      mbar_wait(BAR(MB_URAW));
      TS(48);
      uint4* dst = P.xs + X_UT + (i8 * 64 + g) * (U_CH / 16) + (c & 1) * (U_ODD / 16) + U_PAD / 16 + oct * 8 + w * 2 + (c >> 1);
      uint32_t r[8][4];
#pragma unroll
      for (int i = 0; i < 8; i++) ldsm4t(r[i], sb + OFF_STG0 + w * 4096 + lane * 128 + (((i ^ lane) & 7) << 4));
#pragma unroll
      for (int i = 0; i < 8; i++) dst[i * (U_CH / 2)] = make_uint4(r[i][0], r[i][1], r[i][2], r[i][3]);
      nb_arrive(NB_INIT, 160);
      if (lane == 0) mbar_arrive(BAR(MB_AUX));
      mbar_wait(BAR(MB_EMPTY + 6));
    }
    TS(wg * 16 + 1);
  }

  float acc[2][48];
  {
    uint32_t fb = BAR(MB_FULL) + 64 * wg;
    uint32_t da = (uint32_t)mkdesc(sb + OFF_X, 16, 0, 0) + (wg ? 1024 : 3072), db = (uint32_t)mkdesc(sb + OFF_W, 4096, 0, 0);
    constexpr uint64_t ha = mkdesc(0, 0, 1024, 1), hb = mkdesc(0, 0, 512, 2);
#pragma unroll 1
    for (int kb = 0; kb < 8; kb++) {
      mbar_wait(fb);
      if (kb == 0) TS(wg * 16 + 2);
      WG_FENCE();
#pragma unroll
      for (int k = 0; k < 4; k++) {
        wgmma_ss_n96(acc[0], ha | (da + 2 * k), hb | (db + 64 * k), k ? 1 : kb);
        wgmma_ss_n96(acc[1], ha | (da + 2 * k + 512), hb | (db + 64 * k), k ? 1 : kb);
      }
      WG_COMMIT();
      WG_WAIT(1);
      if (kb > 0 && lane == 0) mbar_arrive(fb + 8 * (MB_EMPTY - MB_FULL - 1));
      fb += 8; db += 768;
      da = da == (uint32_t)mkdesc(sb + OFF_X + 65536, 16, 0, 0) ? da - 4096 : da + 1024;
    }
    WG_WAIT(0);
    if (lane == 0) mbar_arrive(fb + 8 * (MB_EMPTY - MB_FULL - 1));
    mbar_wait(fb + 8 * (MB_EMPTY - MB_FULL - 1));
  }
  TS(wg * 16 + 3);

  constexpr uint32_t stg0 = sb + OFF_STG0, stg1 = sb + OFF_X + 32768;
  const uint32_t sl = (wg ? stg1 : stg0) + w * 3072 + lane * 16;
  uint32_t pw[32], eq[32];
  {
    uint4 af[8];
#pragma unroll
    for (int u = 0; u < 8; u++) {
      const float* a = acc[(u >> 1) & 1] + (u < 4 ? 16 : 0) + 8 * (u & 1);
      af[u] = make_uint4(pack_bf(a[0], a[1]), pack_bf(a[2], a[3]), pack_bf(a[4], a[5]), pack_bf(a[6], a[7]));
    }
    mbar_wait(BAR(MB_AUX));
    float p[8][8];
    WG_FENCE();
#pragma unroll
    for (int u = 0; u < 8; u++) wgmma_rs_n16(p[u], af[u], mkdesc(sb + OFF_PHI + (u & 1) * 512, 128, 256, 0), 0);
    WG_COMMIT();
#pragma unroll
    for (int i = 0; i < 4; i++) {
      const float* a = acc[i >> 1] + 32 + 8 * (i & 1);
      stsm4(sl + (i >> 1) * 12288 + 2048 + (i & 1) * 512, pack_bf(a[0], a[1]), pack_bf(a[2], a[3]), pack_bf(a[4], a[5]), pack_bf(a[6], a[7]));
    }
    WG_WAIT(0);
#pragma unroll
    for (int u = 0; u < 8; u++) {
      pw[4 * u] = pack_bf(p[u][0], p[u][2]); pw[4 * u + 1] = pack_bf(p[u][1], p[u][3]);
      pw[4 * u + 2] = pack_bf(p[u][4], p[u][6]); pw[4 * u + 3] = pack_bf(p[u][5], p[u][7]);
    }
  }
  uint32_t ek[32];
  if (wg == 0) {
#pragma unroll
    for (int i = 0; i < 16; i++) { const uint32_t x = pw[i]; pw[i] = pw[16 + i]; pw[16 + i] = x; }
  }
#pragma unroll 1
  for (int it = 0; it < 2; it++) {
#pragma unroll
    for (int i = 0; i < 32; i++) ek[i] = eq[i];
#pragma unroll
    for (int u = 0; u < 4; u++) dual_exp(pw + 4 * u, eq + 8 * u);
    if (it != wg) {
      TS(wg * 16 + 12);
      mbar_wait(BAR(MB_EMPTY + 15));
#pragma unroll
      for (int i = 0; i < 8; i++) norm_store(eq + 4 * i, sl + (i >> 2) * 12288 + (i & 3) * 512);
      if (wg) nb_arrive(NB_ST0, 256);
    }
#pragma unroll
    for (int i = 0; i < 16; i++) pw[i] = pw[i + 16];
  }
  TS(wg * 16 + 4);
  uint4* const g_part = P.xs + X_PART;
  uint4* const g_o = P.xs + X_O;
  const uint32_t kvs = stg0;
  if (wg == 0) {
#pragma unroll
    for (int i = 0; i < 32; i++) eq[i] = ek[i];
    nb_sync(NB_WG0, 128);
    mbar_wait(BAR(MB_UFULL));
    float kv[12], kw[12];
#pragma unroll
    for (int i = 0; i < 12; i++) kv[i] = kw[i] = 0.f;
    const int mi = lane >> 3;
    const uint32_t ao = w * 512 + (lane & 7) * 16 + ((mi & 1) * 2 + (mi >> 1)) * 128, bo = 2048 + (w >> 1) * 512 + lane * 16;
#pragma unroll 1
    for (int j = 0; j < 2; j++) {
      if (j) nb_sync(NB_ST0, 256);
      const uint32_t sg = j ? stg1 : stg0;
      uint32_t a[8][4], bb[8][4];
#pragma unroll
      for (int s = 0; s < 8; s++) { ldsm4t(a[s], sg + s * 3072 + ao); ldsm4t(bb[s], sg + s * 3072 + bo); }
#pragma unroll
      for (int s = 0; s < 8; s++) {
        float* o = (s & 1) ? kw : kv;
        mma(o[0], o[1], o[2], o[3], a[s][0], a[s][1], a[s][2], a[s][3], bb[s][0], bb[s][1]);
        mma(o[4], o[5], o[6], o[7], a[s][0], a[s][1], a[s][2], a[s][3], bb[s][2], bb[s][3]);
        mma(o[8], o[9], o[10], o[11], a[s][0], a[s][1], a[s][2], a[s][3], 0x3F803F80u, 0x3F803F80u);
      }
    }
#pragma unroll
    for (int i = 0; i < 12; i++) kv[i] += kw[i];
    uint4* pp = g_part + (size_t)(hp * 8 + rt) * 144;
    st_x(pp + t, nz(pack_bf(kv[0], kv[1])), pack_bf(kv[2], kv[3]), pack_bf(kv[4], kv[5]), pack_bf(kv[6], kv[7]));
    if (c < 2) st_x32((uint32_t*)(pp + 128) + w * 16 + c * 8 + g, nz(fu(c ? kv[10] : kv[8])));
    TS(5);
    const uint4* ps = g_part + (size_t)hp * 8 * 144 + t;
    const uint32_t* zs = (const uint32_t*)(g_part + (size_t)(hp * 8 + (lane >> 4) * 4) * 144 + 128) + w * 16 + (lane & 15);
    uint4 v[8];
    uint32_t zv[4];
#pragma unroll 1
    for (int it = 0; it < SPIN_MAX; it++) {
#pragma unroll
      for (int i = 0; i < 8; i++) v[i] = ld_x(ps + i * 144);
#pragma unroll
      for (int i = 0; i < 4; i++) zv[i] = ld_x32(zs + i * 576);
      uint32_t m = min(min(zv[0], zv[1]), min(zv[2], zv[3]));
#pragma unroll
      for (int i = 0; i < 8; i++) m = min(m, v[i].x);
      if (__all_sync(0xffffffffu, m != 0)) break;
    }
    float s4[4][4];
#pragma unroll
    for (int i = 0; i < 4; i++) s4[i][0] = s4[i][1] = s4[i][2] = s4[i][3] = 0.f;
    const uint32_t eye = (g >> 1) == c ? ((g & 1) ? 0x3F800000u : 0x3F80u) : 0u;
#pragma unroll
    for (int r = 0; r < 8; r++) {
      mma_k8(s4[(r & 1) * 2], v[r].x, v[r].y, eye);
      mma_k8(s4[(r & 1) * 2 + 1], v[r].z, v[r].w, eye);
    }
    float s[8];
#pragma unroll
    for (int i = 0; i < 8; i++) s[i] = s4[i >> 2][i & 3] + s4[2 + (i >> 2)][i & 3];
    float zsum = (uf(zv[0]) + uf(zv[1])) + (uf(zv[2]) + uf(zv[3]));
    zsum += __shfl_xor_sync(0xffffffffu, zsum, 16);
    stsm4(kvs + w * 512 + lane * 16, pack_bf(s[0], s[1]), pack_bf(s[2], s[3]), pack_bf(s[4], s[5]), pack_bf(s[6], s[7]));
    sts16(kvs + 2048 + (lane >> 4) * 128 + (w * 16 + (lane & 15)) * 2, lane < 16 ? pack_bf(zsum, 0.f) : 0x3F80u);
    TS(6);
  }
  nb_sync(NB_KV, 256);
  {
    uint32_t kb_[4][4], zb[8];
#pragma unroll
    for (int i = 0; i < 4; i++) ldsm4t(kb_[i], kvs + i * 512 + lane * 16);
#pragma unroll
    for (int i = 0; i < 8; i++) zb[i] = lds32(kvs + 2048 + (g & 1) * 128 + i * 16 + c * 4);
    uint32_t* od = (uint32_t*)(g_o + (size_t)((rt * 4 + wg * 2) * 32 + hp * 2) * 128) + w * 64 + lane;
#pragma unroll
    for (int mt = 0; mt < 2; mt++) {
#pragma unroll
      for (int h = 0; h < 2; h++) {
        const uint32_t* e = eq + 16 * mt + 8 * h;
        float n[8], nm[8], dp[4], dm[4];
        mma0(dp[0], dp[1], dp[2], dp[3], e[0], e[1], e[2], e[3], zb[4 * h], zb[4 * h + 1]);
        mma0(dm[0], dm[1], dm[2], dm[3], e[4], e[5], e[6], e[7], zb[4 * h + 2], zb[4 * h + 3]);
        mma0(n[0], n[1], n[2], n[3], e[0], e[1], e[2], e[3], kb_[2 * h][0], kb_[2 * h][1]);
        mma0(nm[0], nm[1], nm[2], nm[3], e[4], e[5], e[6], e[7], kb_[2 * h + 1][0], kb_[2 * h + 1][1]);
        mma0(n[4], n[5], n[6], n[7], e[0], e[1], e[2], e[3], kb_[2 * h][2], kb_[2 * h][3]);
        mma0(nm[4], nm[5], nm[6], nm[7], e[4], e[5], e[6], e[7], kb_[2 * h + 1][2], kb_[2 * h + 1][3]);
        const float q0 = dp[1] * rcp(dm[1]), q1 = dp[3] * rcp(dm[3]);
        const float r0 = rcp(fmaf(dm[0], q0, fmaf(dp[1], 1e-6f, dp[0]))), r1 = rcp(fmaf(dm[2], q1, fmaf(dp[3], 1e-6f, dp[2])));
#pragma unroll
        for (int i = 0; i < 8; i++) n[i] = fmaf(nm[i], (i & 2) ? q1 : q0, n[i]);
        od[h * 512] = pack_bf(n[0] * r0, n[1] * r0);
        od[h * 512 + 32] = pack_bf(n[2] * r1, n[3] * r1);
        od[h * 512 + 256] = pack_bf(n[4] * r0, n[5] * r0);
        od[h * 512 + 288] = pack_bf(n[6] * r1, n[7] * r1);
      }
      od += 16384;
    }
  }
  TS(wg * 16 + 7);
  nb_arrive(NB_ODONE, 320);
  if (wg) return;
  mbar_wait(BAR(MB_WO));
  mbar_wait(BAR(MB_OA));
  TS(8);
  nb_sync(NB_BDONE, 288);
  TS(9);
  float oc[64];
  {
    constexpr uint64_t ha = mkdesc(0, 0, 128, 0), hb = mkdesc(0, 0, 1024, 1);
    constexpr uint32_t da0 = (uint32_t)mkdesc(stg1, 1024, 0, 0), db0 = (uint32_t)mkdesc(sb + OFF_W, 8192, 0, 0);
#pragma unroll 1
    for (int j = 0; j < 8; j++) {
      const int kb = (j + 7) & 7;
      if ((j & 3) == 1) mbar_wait(j == 1 ? BAR(MB_OC) : BAR(MB_OB));
      WG_FENCE();
#pragma unroll
      for (int k = 0; k < 4; k++) wgmma_ss_n128(oc, ha | (da0 + 512 * kb + 128 * k), hb | (db0 + 1024 * kb + 128 * k), k ? 1 : j);
      WG_COMMIT();
    }
    WG_WAIT(0);
  }
  TS(10);
  nb_sync(NB_WG0, 128);
  const uint32_t ot = sb + OFF_W + w * 4096;
#pragma unroll
  for (int i = 0; i < 16; i += 2)
    stsm4(ot + (i >> 3) * 2048 + (lane & 15) * 128 + (((i + (lane >> 4)) ^ lane) & 7) * 16, pack_bf(oc[4 * i], oc[4 * i + 1]),
          pack_bf(oc[4 * i + 2], oc[4 * i + 3]), pack_bf(oc[4 * i + 4], oc[4 * i + 5]), pack_bf(oc[4 * i + 6], oc[4 * i + 7]));
  asm volatile("fence.proxy.async.shared::cta;" ::: "memory");
  __syncwarp();
  e_store3d(&mout, ot, (rt * 4 + (hp >> 2)) * 64 + w * 16, (hp & 3) * 2);
  TS(wg * 16 + 11);
  GT(61 + wg);
}

typedef CUresult (*EncodeFn)(CUtensorMap*, CUtensorMapDataType, cuuint32_t, void*, const cuuint64_t*, const cuuint64_t*,
                             const cuuint32_t*, const cuuint32_t*, CUtensorMapInterleave, CUtensorMapSwizzle,
                             CUtensorMapL2promotion, CUtensorMapFloatOOBfill);

}

extern "C" void kernel_launch(void* const* d_in, const int* in_sizes, int n_in, void* d_out, int out_size) {
  (void)in_sizes; (void)n_in; (void)out_size;
  void* fn = nullptr;
  cudaDriverEntryPointQueryResult qr;
  cudaGetDriverEntryPoint("cuTensorMapEncodeTiled", &fn, cudaEnableDefault, &qr);
  EncodeFn enc = (EncodeFn)fn;
  CUtensorMap mx, mw, mo, mu, mout;
  const cuuint32_t es[5] = {1, 1, 1, 1, 1};
  {
    cuuint64_t dims[2] = {512, 2048}, st[1] = {1024};
    cuuint32_t box[2] = {64, 128};
    enc(&mx, CU_TENSOR_MAP_DATA_TYPE_BFLOAT16, 2, d_in[0], dims, st, box, es, CU_TENSOR_MAP_INTERLEAVE_NONE,
        CU_TENSOR_MAP_SWIZZLE_128B, CU_TENSOR_MAP_L2_PROMOTION_L2_128B, CU_TENSOR_MAP_FLOAT_OOB_FILL_NONE);
  }
  {
    cuuint64_t dims[3] = {512, 512, 3}, st[2] = {3072, 1024};
    cuuint32_t box[3] = {32, 64, 3};
    enc(&mw, CU_TENSOR_MAP_DATA_TYPE_BFLOAT16, 3, d_in[1], dims, st, box, es, CU_TENSOR_MAP_INTERLEAVE_NONE,
        CU_TENSOR_MAP_SWIZZLE_64B, CU_TENSOR_MAP_L2_PROMOTION_L2_128B, CU_TENSOR_MAP_FLOAT_OOB_FILL_NONE);
  }
  {
    cuuint64_t dims[3] = {64, 512, 8}, st[2] = {1024, 128};
    cuuint32_t box[3] = {64, 64, 2};
    enc(&mo, CU_TENSOR_MAP_DATA_TYPE_BFLOAT16, 3, d_in[3], dims, st, box, es, CU_TENSOR_MAP_INTERLEAVE_NONE,
        CU_TENSOR_MAP_SWIZZLE_128B, CU_TENSOR_MAP_L2_PROMOTION_L2_128B, CU_TENSOR_MAP_FLOAT_OOB_FILL_NONE);
  }
  {
    cuuint64_t dims[5] = {512, 2, 4, 4, 64}, st[4] = {1024, 8192, 2048, 32768};
    cuuint32_t box[5] = {64, 2, 4, 4, 4};
    enc(&mu, CU_TENSOR_MAP_DATA_TYPE_BFLOAT16, 5, d_in[4], dims, st, box, es, CU_TENSOR_MAP_INTERLEAVE_NONE,
        CU_TENSOR_MAP_SWIZZLE_128B, CU_TENSOR_MAP_L2_PROMOTION_L2_128B, CU_TENSOR_MAP_FLOAT_OOB_FILL_NONE);
  }
  {
    cuuint64_t dims[3] = {64, 2048, 16}, st[2] = {2048, 128};
    cuuint32_t box[3] = {64, 16, 2};
    enc(&mout, CU_TENSOR_MAP_DATA_TYPE_BFLOAT16, 3, d_out, dims, st, box, es, CU_TENSOR_MAP_INTERLEAVE_NONE,
        CU_TENSOR_MAP_SWIZZLE_128B, CU_TENSOR_MAP_L2_PROMOTION_NONE, CU_TENSOR_MAP_FLOAT_OOB_FILL_NONE);
  }
  Params P;
  P.x = (const __nv_bfloat16*)d_in[0];
  P.wphi = (const __nv_bfloat16*)d_in[2];
  P.wo = (const __nv_bfloat16*)d_in[3];
  P.logA = (const __nv_bfloat16*)d_in[5];
  P.Aim = (const __nv_bfloat16*)d_in[6];
  P.Cre = (const __nv_bfloat16*)d_in[7];
  P.Cim = (const __nv_bfloat16*)d_in[8];
  P.logdt = (const __nv_bfloat16*)d_in[9];
  P.Dskip = (const __nv_bfloat16*)d_in[10];
  P.out = (__nv_bfloat16*)d_out;
  cudaGetSymbolAddress((void**)&P.xs, g_x);
  P.ts = nullptr;
  cudaFuncSetAttribute(fused_kernel, cudaFuncAttributeMaxDynamicSharedMemorySize, SMEM_BYTES);
  fused_kernel<<<NCTA, NTHREADS, SMEM_BYTES>>>(P, mx, mw, mo, mu, mout);
}
```

```cpp
#include <cuda_runtime.h>
#include <cuda_bf16.h>
#include <cuda_fp16.h>
#include <cuda.h>
#include <stdint.h>

#define DBG_TS 0

namespace {

constexpr int NTHREADS = 512;
constexpr int NCTA = 128;
constexpr int OFF_W = 0;
constexpr int OFF_X = 98304;
constexpr int OFF_U = OFF_X + 65536;
constexpr int U_CH = 4416, U_ODD = 2240, U_PAD = 128;
constexpr int OFF_STG0 = OFF_U + 18432;
constexpr int OFF_T = OFF_STG0 + 24576;
constexpr int T_CH = 5216;
constexpr int T_D = 0;
constexpr int T_5 = 2144;
constexpr int T_3 = T_5 + 384;
constexpr int T_7 = T_5 + 1024;
constexpr int T_9 = T_7 + 320;
constexpr int T_KC = T_9 + 320;
constexpr int T_ST = T_5 - 1024;
constexpr int OFF_PHI = OFF_T + 4 * T_CH;
constexpr int OFF_BAR = OFF_PHI + 1024;
constexpr int SMEM_BYTES = OFF_BAR + 512;
constexpr uint32_t SB = 1024;
static_assert(T_KC + 2 * 656 <= T_CH, "table size");
static_assert(SMEM_BYTES <= 232448, "smem");
constexpr int MB_URAW = 0, MB_FULL = 1  , MB_WO = 17, MB_UFULL = 18, MB_OA = 19, MB_OB = 20, MB_OC = 21,
              MB_EMPTY = 22  , MB_AUX = 38;
__host__ __device__ constexpr uint32_t BAR(int i) { return SB + OFF_BAR + 8 * i; }
constexpr int NB_WG0 = 1, NB_ODONE = 2, NB_ST0 = 3  , NB_KV = 5, NB_YZ = 6, NB_INIT = 7, NB_PREP = 8, NB_PROD = 9, NB_KREAD = 10, NB_BDONE = 11, NB_ZERO = 12;
#define ZERO_N 1024
#define ZERO_STEP 7
#define STEPU 3
#define STEPPF 0
constexpr int STEP_PF = STEPPF, STEP_U = STEPU;
constexpr int SPIN_MAX = 1 << 16;

constexpr int X_CNT = 0;
constexpr int X_PART = 128;
constexpr int X_O = X_PART + 16 * 8 * 144;
constexpr int X_Y = X_O + 32 * 32 * 128;
constexpr int X_UT = X_Y + 512 * 8 * 32;
constexpr int X_SIZE = X_UT + 512 * (U_CH / 16);
__device__ __align__(128) uint4 g_x[X_SIZE];
extern __shared__ uint8_t smem_raw[];
#define TS(i) do {} while (0)
#define TS1(i) do {} while (0)
#define GT(i) do {} while (0)

__device__ __forceinline__ uint32_t smem_u32(const void* p) { return (uint32_t)__cvta_generic_to_shared(p); }
__device__ __forceinline__ void mbar_arrive(uint32_t b) {
  asm volatile("mbarrier.arrive.shared::cta.b64 _, [%0];" ::"r"(b) : "memory");
}
__device__ __forceinline__ void mbar_wait(uint32_t b) {
  uint32_t done = 0;
#pragma unroll 1
  for (int i = 0; i < SPIN_MAX && !done; i++) {
    asm volatile("{\n.reg .pred p;\nmbarrier.try_wait.parity.shared::cta.b64 p, [%1], 0, 4000;\nselp.u32 %0, 1, 0, p;\n}\n"
                 : "=r"(done) : "r"(b) : "memory");
  }
}
__device__ __forceinline__ void mbar_init(uint32_t b, int n) {
  asm volatile("mbarrier.init.shared::cta.b64 [%0], %1;" ::"r"(b), "r"(n) : "memory");
}
__device__ __forceinline__ void mbar_expect(uint32_t b, int bytes) {
  asm volatile("mbarrier.arrive.expect_tx.shared::cta.b64 _, [%0], %1;" ::"r"(b), "r"(bytes) : "memory");
}
__device__ __forceinline__ void nb_sync(int id, int n) { asm volatile("bar.sync %0, %1;" ::"r"(id), "r"(n) : "memory"); }
__device__ __forceinline__ void nb_arrive(int id, int n) { asm volatile("bar.arrive %0, %1;" ::"r"(id), "r"(n) : "memory"); }
#define ELECT "{\n.reg .pred p;\nelect.sync _|p, 0xffffffff;\n@p "
__device__ __forceinline__ void e_expect(uint32_t b, int bytes) {
  asm volatile(ELECT "mbarrier.arrive.expect_tx.shared::cta.b64 _, [%0], %1;\n}\n" ::"r"(b), "r"(bytes) : "memory");
}
__device__ __forceinline__ void e_tma2d(uint32_t dst, const CUtensorMap* m, uint32_t bar, int c0, int c1) {
  asm volatile(ELECT "cp.async.bulk.tensor.2d.shared::cluster.global.mbarrier::complete_tx::bytes [%0], [%1, {%3,%4}], [%2];\n}\n"
               ::"r"(dst), "l"(m), "r"(bar), "r"(c0), "r"(c1) : "memory");
}
__device__ __forceinline__ void e_tma3d(uint32_t dst, const CUtensorMap* m, uint32_t bar, int c0, int c1, int c2) {
  asm volatile(ELECT "cp.async.bulk.tensor.3d.shared::cluster.global.mbarrier::complete_tx::bytes [%0], [%1, {%3,%4,%5}], [%2];\n}\n"
               ::"r"(dst), "l"(m), "r"(bar), "r"(c0), "r"(c1), "r"(c2) : "memory");
}
__device__ __forceinline__ void e_tma5d(uint32_t dst, const CUtensorMap* m, uint32_t bar, int c0, int c4) {
  asm volatile(ELECT "cp.async.bulk.tensor.5d.shared::cluster.global.mbarrier::complete_tx::bytes [%0], [%1, {%3,%5,%5,%5,%4}], [%2];\n}\n"
               ::"r"(dst), "l"(m), "r"(bar), "r"(c0), "r"(c4), "r"(0) : "memory");
}
__device__ __forceinline__ void e_bulk(uint32_t dst, const void* src, int bytes, uint32_t bar) {
  asm volatile(ELECT "cp.async.bulk.shared::cluster.global.mbarrier::complete_tx::bytes [%0], [%1], %2, [%3];\n}\n"
               ::"r"(dst), "l"(src), "r"(bytes), "r"(bar) : "memory");
}
__device__ __forceinline__ void e_prefetch(const void* p, int bytes) {
  asm volatile(ELECT "cp.async.bulk.prefetch.L2.global [%0], %1;\n}\n" ::"l"(p), "r"(bytes) : "memory");
}
__device__ __forceinline__ void e_store3d(const CUtensorMap* m, uint32_t src, int c1, int c2) {
  asm volatile(ELECT "cp.async.bulk.tensor.3d.global.shared::cta.bulk_group [%0, {%4,%2,%3}], [%1];\n"
               "@p cp.async.bulk.commit_group;\n@p cp.async.bulk.wait_group.read 0;\n}\n"
               ::"l"(m), "r"(src), "r"(c1), "r"(c2), "r"(0) : "memory");
}
__host__ __device__ constexpr uint64_t mkdesc(uint32_t addr, uint32_t lbo, uint32_t sbo, int swz) {
  return (uint64_t)((addr & 0x3FFFF) >> 4) | ((uint64_t)(lbo >> 4) << 16) | ((uint64_t)(sbo >> 4) << 32) |
         ((uint64_t)swz << 62);
}
#define WG_FENCE() asm volatile("wgmma.fence.sync.aligned;" ::: "memory")
#define WG_COMMIT() asm volatile("wgmma.commit_group.sync.aligned;" ::: "memory")
#define WG_WAIT(n) asm volatile("wgmma.wait_group.sync.aligned " #n ";" ::: "memory")

__device__ __forceinline__ void mma(float& d0, float& d1, float& d2, float& d3, uint32_t a0, uint32_t a1, uint32_t a2,
                                    uint32_t a3, uint32_t b0, uint32_t b1) {
  asm volatile("mma.sync.aligned.m16n8k16.row.col.f32.bf16.bf16.f32 {%0,%1,%2,%3},{%4,%5,%6,%7},{%8,%9},{%0,%1,%2,%3};"
               : "+f"(d0), "+f"(d1), "+f"(d2), "+f"(d3)
               : "r"(a0), "r"(a1), "r"(a2), "r"(a3), "r"(b0), "r"(b1));
}
__device__ __forceinline__ void mmac(float (&d)[4], uint32_t a0, uint32_t a1, uint32_t a2, uint32_t a3, uint32_t b0,
                                     uint32_t b1, const float (&c)[4]) {
  asm volatile("mma.sync.aligned.m16n8k16.row.col.f32.bf16.bf16.f32 {%0,%1,%2,%3},{%4,%5,%6,%7},{%8,%9},{%10,%11,%12,%13};"
               : "=f"(d[0]), "=f"(d[1]), "=f"(d[2]), "=f"(d[3])
               : "r"(a0), "r"(a1), "r"(a2), "r"(a3), "r"(b0), "r"(b1), "f"(c[0]), "f"(c[1]), "f"(c[2]), "f"(c[3]));
}
__device__ __forceinline__ void mma_p(int p, float (&d)[4], uint32_t a0, uint32_t a1, uint32_t a2, uint32_t a3, uint32_t b0, uint32_t b1) {
  asm volatile("{\n.reg .pred q;\nsetp.ne.b32 q, %10, 0;\n"
               "@q mma.sync.aligned.m16n8k16.row.col.f32.bf16.bf16.f32 {%0,%1,%2,%3},{%4,%5,%6,%7},{%8,%9},{%0,%1,%2,%3};\n}\n"
               : "+f"(d[0]), "+f"(d[1]), "+f"(d[2]), "+f"(d[3])
               : "r"(a0), "r"(a1), "r"(a2), "r"(a3), "r"(b0), "r"(b1), "r"(p));
}
__device__ __forceinline__ void mmac_p(int p, float (&d)[4], uint32_t a0, uint32_t a1, uint32_t a2, uint32_t a3, uint32_t b0,
                                       uint32_t b1, const float (&c)[4]) {
  asm volatile("{\n.reg .pred q;\nsetp.ne.b32 q, %14, 0;\n"
               "@q mma.sync.aligned.m16n8k16.row.col.f32.bf16.bf16.f32 {%0,%1,%2,%3},{%4,%5,%6,%7},{%8,%9},{%10,%11,%12,%13};\n}\n"
               : "+f"(d[0]), "+f"(d[1]), "+f"(d[2]), "+f"(d[3])
               : "r"(a0), "r"(a1), "r"(a2), "r"(a3), "r"(b0), "r"(b1), "f"(c[0]), "f"(c[1]), "f"(c[2]), "f"(c[3]), "r"(p));
}
__device__ __forceinline__ void mma_h(float (&d)[4], const uint32_t (&a)[4], uint32_t b0, uint32_t b1) {
  asm volatile("mma.sync.aligned.m16n8k16.row.col.f32.f16.f16.f32 {%0,%1,%2,%3},{%4,%5,%6,%7},{%8,%9},{%0,%1,%2,%3};"
               : "+f"(d[0]), "+f"(d[1]), "+f"(d[2]), "+f"(d[3]) : "r"(a[0]), "r"(a[1]), "r"(a[2]), "r"(a[3]), "r"(b0), "r"(b1));
}
__device__ __forceinline__ void mma_k8(float (&d)[4], uint32_t a0, uint32_t a1, uint32_t b0) {
  asm volatile("mma.sync.aligned.m16n8k8.row.col.f32.bf16.bf16.f32 {%0,%1,%2,%3},{%4,%5},{%6},{%0,%1,%2,%3};"
               : "+f"(d[0]), "+f"(d[1]), "+f"(d[2]), "+f"(d[3]) : "r"(a0), "r"(a1), "r"(b0));
}
__device__ __forceinline__ void mma0(float& d0, float& d1, float& d2, float& d3, uint32_t a0, uint32_t a1, uint32_t a2,
                                     uint32_t a3, uint32_t b0, uint32_t b1) {
  asm volatile("mma.sync.aligned.m16n8k16.row.col.f32.bf16.bf16.f32 {%0,%1,%2,%3},{%4,%5,%6,%7},{%8,%9},{%10,%10,%10,%10};"
               : "=f"(d0), "=f"(d1), "=f"(d2), "=f"(d3)
               : "r"(a0), "r"(a1), "r"(a2), "r"(a3), "r"(b0), "r"(b1), "f"(0.f));
}
__device__ __forceinline__ uint32_t pack_bf(float lo, float hi) {
  uint32_t r;
  asm("cvt.rn.bf16x2.f32 %0, %1, %2;" : "=r"(r) : "f"(hi), "f"(lo));
  return r;
}
__device__ __forceinline__ float bf_lo(uint32_t w) { return __uint_as_float(w << 16); }
__device__ __forceinline__ float bf_hi(uint32_t w) { return __uint_as_float(w & 0xffff0000u); }
__device__ __forceinline__ float bf_round(float x) { return __bfloat162float(__float2bfloat16_rn(x)); }
__device__ __forceinline__ uint32_t bmax2(uint32_t a, uint32_t b) {
  uint32_t r; asm("max.bf16x2 %0, %1, %2;" : "=r"(r) : "r"(a), "r"(b)); return r;
}
__device__ __forceinline__ uint32_t bmin2(uint32_t a, uint32_t b) {
  uint32_t r; asm("min.bf16x2 %0, %1, %2;" : "=r"(r) : "r"(a), "r"(b)); return r;
}
__device__ __forceinline__ float ex2(float x) { float r; asm("ex2.approx.ftz.f32 %0, %1;" : "=f"(r) : "f"(x)); return r; }
__device__ __forceinline__ float rcp(float x) { float r; asm("rcp.approx.ftz.f32 %0, %1;" : "=f"(r) : "f"(x)); return r; }
__device__ __forceinline__ void ldsm4(uint32_t (&r)[4], uint32_t a) {
  asm volatile("ldmatrix.sync.aligned.m8n8.x4.shared.b16 {%0,%1,%2,%3}, [%4];"
               : "=r"(r[0]), "=r"(r[1]), "=r"(r[2]), "=r"(r[3]) : "r"(a) : "memory");
}
__device__ __forceinline__ void ldsm4t(uint32_t (&r)[4], uint32_t a) {
  asm volatile("ldmatrix.sync.aligned.m8n8.x4.trans.shared.b16 {%0,%1,%2,%3}, [%4];"
               : "=r"(r[0]), "=r"(r[1]), "=r"(r[2]), "=r"(r[3]) : "r"(a) : "memory");
}
__device__ __forceinline__ void stsm4(uint32_t a, uint32_t r0, uint32_t r1, uint32_t r2, uint32_t r3) {
  asm volatile("stmatrix.sync.aligned.m8n8.x4.shared.b16 [%0], {%1,%2,%3,%4};"
               ::"r"(a), "r"(r0), "r"(r1), "r"(r2), "r"(r3) : "memory");
}
__device__ __forceinline__ uint32_t lds32(uint32_t a) {
  uint32_t r; asm volatile("ld.shared.u32 %0, [%1];" : "=r"(r) : "r"(a) : "memory"); return r;
}
__device__ __forceinline__ uint32_t lds16(uint32_t a) {
  uint32_t r; asm volatile("{\n.reg .u16 h;\nld.shared.u16 h, [%1];\ncvt.u32.u16 %0, h;\n}\n" : "=r"(r) : "r"(a) : "memory"); return r;
}
__device__ __forceinline__ uint2 lds64(uint32_t a) {
  uint2 r; asm volatile("ld.shared.v2.u32 {%0,%1}, [%2];" : "=r"(r.x), "=r"(r.y) : "r"(a) : "memory"); return r;
}
__device__ __forceinline__ uint4 lds128(uint32_t a) {
  uint4 r;
  asm volatile("ld.shared.v4.u32 {%0,%1,%2,%3}, [%4];" : "=r"(r.x), "=r"(r.y), "=r"(r.z), "=r"(r.w) : "r"(a) : "memory");
  return r;
}
__device__ __forceinline__ void sts32(uint32_t a, uint32_t v) { asm volatile("st.shared.u32 [%0], %1;" ::"r"(a), "r"(v) : "memory"); }
__device__ __forceinline__ void sts16(uint32_t a, uint32_t v) {
  asm volatile("{\n.reg .u16 h;\ncvt.u16.u32 h, %1;\nst.shared.u16 [%0], h;\n}\n" ::"r"(a), "r"(v) : "memory");
}
__device__ __forceinline__ void sts64(uint32_t a, uint32_t x, uint32_t y) {
  asm volatile("st.shared.v2.u32 [%0], {%1,%2};" ::"r"(a), "r"(x), "r"(y) : "memory");
}
__device__ __forceinline__ void sts128(uint32_t a, uint32_t x, uint32_t y, uint32_t z, uint32_t w) {
  asm volatile("st.shared.v4.u32 [%0], {%1,%2,%3,%4};" ::"r"(a), "r"(x), "r"(y), "r"(z), "r"(w) : "memory");
}
__device__ __forceinline__ uint4 ld_x(const uint4* p) {
  uint4 r;
  asm volatile("{\n.reg .b128 t;\nld.relaxed.gpu.global.b128 t, [%4];\nmov.b128 {%0,%1,%2,%3}, t;\n}\n"
               : "=r"(r.x), "=r"(r.y), "=r"(r.z), "=r"(r.w) : "l"(p) : "memory");
  return r;
}
__device__ __forceinline__ uint32_t ld_x32(const uint32_t* p) {
  uint32_t r; asm volatile("ld.relaxed.gpu.global.u32 %0, [%1];" : "=r"(r) : "l"(p) : "memory"); return r;
}
__device__ __forceinline__ void st_x(uint4* p, uint32_t x, uint32_t y, uint32_t z, uint32_t w) {
  asm volatile("{\n.reg .b128 t;\nmov.b128 t, {%1,%2,%3,%4};\nst.relaxed.gpu.global.b128 [%0], t;\n}\n"
               ::"l"(p), "r"(x), "r"(y), "r"(z), "r"(w) : "memory");
}
__device__ __forceinline__ void st_x_p(int p, uint4* a, uint32_t x, uint32_t y, uint32_t z, uint32_t w) {
  asm volatile("{\n.reg .b128 t;\n.reg .pred q;\nsetp.ne.b32 q, %5, 0;\nmov.b128 t, {%1,%2,%3,%4};\n@q st.relaxed.gpu.global.b128 [%0], t;\n}\n"
               ::"l"(a), "r"(x), "r"(y), "r"(z), "r"(w), "r"(p) : "memory");
}
__device__ __forceinline__ void sts64_p(int p, uint32_t a, uint32_t x, uint32_t y) {
  asm volatile("{\n.reg .pred q;\nsetp.ne.b32 q, %3, 0;\n@q st.shared.v2.u32 [%0], {%1,%2};\n}\n" ::"r"(a), "r"(x), "r"(y), "r"(p) : "memory");
}
__device__ __forceinline__ void st_x32(uint32_t* p, uint32_t x) {
  asm volatile("st.relaxed.gpu.global.u32 [%0], %1;" ::"l"(p), "r"(x) : "memory");
}
__device__ __forceinline__ uint32_t nz(uint32_t w) { return max(w, 1u); }
__device__ __forceinline__ uint32_t fu(float x) { return __float_as_uint(x); }
__device__ __forceinline__ float uf(uint32_t x) { return __uint_as_float(x); }

__device__ __forceinline__ void wgmma_ss_n96(float (&d)[48], uint64_t da, uint64_t db, int sc) {
  asm volatile("{\n.reg .pred p;\nsetp.ne.b32 p, %50, 0;\n"
      "wgmma.mma_async.sync.aligned.m64n96k16.f32.bf16.bf16 "
      "{%0,%1,%2,%3,%4,%5,%6,%7,%8,%9,%10,%11,%12,%13,%14,%15,%16,%17,%18,%19,%20,%21,%22,%23,%24,%25,%26,%27,%28,%29,%30,%31,%32,%33,%34,%35,%36,%37,%38,%39,%40,%41,%42,%43,%44,%45,%46,%47}, "
      "%48, %49, p, 1, 1, 0, 1;\n}\n"
      : "+f"(d[0]), "+f"(d[1]), "+f"(d[2]), "+f"(d[3]), "+f"(d[4]), "+f"(d[5]), "+f"(d[6]), "+f"(d[7]),
        "+f"(d[8]), "+f"(d[9]), "+f"(d[10]), "+f"(d[11]), "+f"(d[12]), "+f"(d[13]), "+f"(d[14]), "+f"(d[15]),
        "+f"(d[16]), "+f"(d[17]), "+f"(d[18]), "+f"(d[19]), "+f"(d[20]), "+f"(d[21]), "+f"(d[22]), "+f"(d[23]),
        "+f"(d[24]), "+f"(d[25]), "+f"(d[26]), "+f"(d[27]), "+f"(d[28]), "+f"(d[29]), "+f"(d[30]), "+f"(d[31]),
        "+f"(d[32]), "+f"(d[33]), "+f"(d[34]), "+f"(d[35]), "+f"(d[36]), "+f"(d[37]), "+f"(d[38]), "+f"(d[39]),
        "+f"(d[40]), "+f"(d[41]), "+f"(d[42]), "+f"(d[43]), "+f"(d[44]), "+f"(d[45]), "+f"(d[46]), "+f"(d[47])
      : "l"(da), "l"(db), "r"(sc));
}

__device__ __forceinline__ void wgmma_ss_n128(float (&d)[64], uint64_t da, uint64_t db, int sc) {
  asm volatile("{\n.reg .pred p;\nsetp.ne.b32 p, %66, 0;\n"
      "wgmma.mma_async.sync.aligned.m64n128k16.f32.bf16.bf16 "
      "{%0,%1,%2,%3,%4,%5,%6,%7,%8,%9,%10,%11,%12,%13,%14,%15,%16,%17,%18,%19,%20,%21,%22,%23,%24,%25,%26,%27,%28,%29,%30,%31,%32,%33,%34,%35,%36,%37,%38,%39,%40,%41,%42,%43,%44,%45,%46,%47,%48,%49,%50,%51,%52,%53,%54,%55,%56,%57,%58,%59,%60,%61,%62,%63}, "
      "%64, %65, p, 1, 1, 0, 1;\n}\n"
      : "+f"(d[0]), "+f"(d[1]), "+f"(d[2]), "+f"(d[3]), "+f"(d[4]), "+f"(d[5]), "+f"(d[6]), "+f"(d[7]),
        "+f"(d[8]), "+f"(d[9]), "+f"(d[10]), "+f"(d[11]), "+f"(d[12]), "+f"(d[13]), "+f"(d[14]), "+f"(d[15]),
        "+f"(d[16]), "+f"(d[17]), "+f"(d[18]), "+f"(d[19]), "+f"(d[20]), "+f"(d[21]), "+f"(d[22]), "+f"(d[23]),
        "+f"(d[24]), "+f"(d[25]), "+f"(d[26]), "+f"(d[27]), "+f"(d[28]), "+f"(d[29]), "+f"(d[30]), "+f"(d[31]),
        "+f"(d[32]), "+f"(d[33]), "+f"(d[34]), "+f"(d[35]), "+f"(d[36]), "+f"(d[37]), "+f"(d[38]), "+f"(d[39]),
        "+f"(d[40]), "+f"(d[41]), "+f"(d[42]), "+f"(d[43]), "+f"(d[44]), "+f"(d[45]), "+f"(d[46]), "+f"(d[47]),
        "+f"(d[48]), "+f"(d[49]), "+f"(d[50]), "+f"(d[51]), "+f"(d[52]), "+f"(d[53]), "+f"(d[54]), "+f"(d[55]),
        "+f"(d[56]), "+f"(d[57]), "+f"(d[58]), "+f"(d[59]), "+f"(d[60]), "+f"(d[61]), "+f"(d[62]), "+f"(d[63])
      : "l"(da), "l"(db), "r"(sc));
}

__device__ __forceinline__ void wgmma_rs_n16(float (&d)[8], const uint4& a, uint64_t db, int sc) {
  asm volatile("{\n.reg .pred p;\nsetp.ne.b32 p, %13, 0;\n"
      "wgmma.mma_async.sync.aligned.m64n16k16.f32.bf16.bf16 "
      "{%0,%1,%2,%3,%4,%5,%6,%7}, "
      "{%8,%9,%10,%11}, %12, p, 1, 1, 1;\n}\n"
      : "+f"(d[0]), "+f"(d[1]), "+f"(d[2]), "+f"(d[3]), "+f"(d[4]), "+f"(d[5]), "+f"(d[6]), "+f"(d[7])
      : "r"(a.x), "r"(a.y), "r"(a.z), "r"(a.w), "l"(db), "r"(sc));
}

struct Params {
  const __nv_bfloat16 *logA, *Aim, *Cre, *Cim, *logdt, *Dskip, *x, *wqkv, *wphi, *wo;
  __nv_bfloat16* out;
  uint4* xs;
  long long* ts;
};

__device__ __forceinline__ uint4 tr_row(const uint4 (&v)[8], int i) {
  uint32_t o[4];
#pragma unroll
  for (int m = 0; m < 4; m++) {
    const uint4 &ra = v[2 * m], &rb = v[2 * m + 1];
    const int k = i >> 1;
    const uint32_t xa = k == 0 ? ra.x : k == 1 ? ra.y : k == 2 ? ra.z : ra.w;
    const uint32_t xb = k == 0 ? rb.x : k == 1 ? rb.y : k == 2 ? rb.z : rb.w;
    o[m] = __byte_perm(xa, xb, (i & 1) ? 0x7632 : 0x5410);
  }
  return make_uint4(o[0], o[1], o[2], o[3]);
}

struct cpx { float r, i; };
__device__ __forceinline__ cpx csq(cpx a) { return {a.r * a.r - a.i * a.i, 2.f * (a.r * a.i)}; }
__device__ __forceinline__ cpx polar(float e, float t) {
  const float m = ex2(e);
  return {m * __cosf(t), m * __sinf(t)};
}

struct KgenRaw { unsigned short la, ai, cr, ci, ldt; };
__device__ __forceinline__ KgenRaw kgen_load(const Params& P, int d, int unit, int lane) {
  const int o = d * 128 + unit * 32 + lane;
  return {__ldg((const unsigned short*)P.logA + o), __ldg((const unsigned short*)P.Aim + o), __ldg((const unsigned short*)P.Cre + o),
          __ldg((const unsigned short*)P.Cim + o), __ldg((const unsigned short*)P.logdt + d)};
}
struct hmul { __half2 a, b; };
__device__ __forceinline__ hmul mk_mul(cpx w) { return {__floats2half2_rn(w.r, w.i), __floats2half2_rn(-w.i, w.r)}; }
__device__ __forceinline__ __half2 hcm(__half2 z, const hmul& w) { return __hfma2(__high2half2(z), w.b, __hmul2(__low2half2(z), w.a)); }
__device__ __forceinline__ uint32_t hu(__half2 v) { return *(const uint32_t*)&v; }

__device__ __forceinline__ void kgen_unit(const KgenRaw& r, int lane, uint32_t buf, float (&k)[5][4], float& k2048) {
  const float dt = bf_round(expf(bf_lo(r.ldt)));
  const float a2 = -(bf_round(expf(bf_lo(r.la))) * dt) * 1.4426950408889634f;
  const float f = bf_lo(r.ai) * dt;
  const float r128 = f * 20.371832715762604f;
  const uint32_t ex = min(max(__reduce_max_sync(0xffffffffu, max(r.cr & 0x7fffu, r.ci & 0x7fffu)) >> 7, 1u), 253u);
  const float cs = uf((254u - ex) << 23), sc = 2.f * dt * uf(ex << 23);
  const cpx C = {bf_lo(r.cr) * cs, -bf_lo(r.ci) * cs};
  const uint32_t sa = buf + (lane & 7) * 128 + ((((lane >> 3) ^ lane) & 7) << 4);
  const uint32_t lb = buf + (lane >> 3) * 128 + (((lane ^ (lane >> 3)) & 7) << 4);
  const uint32_t la = buf + ((lane >> 3) & 1) * 1024 + (lane >> 4) * 128 + (((lane ^ (lane >> 4)) & 7) << 4);
  auto put = [&](const __half2 (&v)[8], uint32_t off) {
    stsm4(sa + off, hu(v[0]), hu(v[1]), hu(v[2]), hu(v[3]));
    stsm4((sa ^ 64) + off, hu(v[4]), hu(v[5]), hu(v[6]), hu(v[7]));
  };
  uint32_t A[4][4];
  auto tile = [&](int j, uint32_t off) {
    uint32_t B[2][4];
    __syncwarp();
    ldsm4(B[0], lb + off);
    ldsm4(B[1], (lb ^ 64) + 512 + off);
    k[j][0] = k[j][1] = k[j][2] = k[j][3] = 0.f;
#pragma unroll
    for (int s = 0; s < 4; s++) mma_h(k[j], A[s], B[s >> 1][2 * (s & 1)], B[s >> 1][2 * (s & 1) + 1]);
  };
  const cpx w1 = polar(a2, f), w128 = polar(a2 * 128.f, (r128 - rintf(r128)) * 6.283185307179586f);
  const cpx w2 = csq(w1), w4 = csq(w2), w256 = csq(w128), w512 = csq(w256), w1024 = csq(w512), we = csq(w1024);
  k2048 = (C.r * we.r + C.i * we.i) * sc;
  {
    cpx w8 = csq(w4);
    w8.i = -w8.i;
    const cpx w16 = csq(w8), w32 = csq(w16), w64 = csq(w32);
    const hmul m8 = mk_mul(w8), m16 = mk_mul(w16), m32 = mk_mul(w32), m64 = mk_mul(w64);
    __half2 a[8];
    a[0] = __floats2half2_rn(C.r, C.i); a[1] = hcm(a[0], m8);
    a[2] = hcm(a[0], m16); a[3] = hcm(a[1], m16);
#pragma unroll
    for (int i = 0; i < 4; i++) a[4 + i] = hcm(a[i], m32);
    put(a, 0);
#pragma unroll
    for (int i = 0; i < 8; i++) a[i] = hcm(a[i], m64);
    put(a, 1024);
    __syncwarp();
#pragma unroll
    for (int s = 0; s < 4; s++) ldsm4(A[s], (la ^ (s << 5)) + s * 256);
  }
  __half2 t0[8], t1[8], t2[8], t3[8], t4[8];
  const hmul m2 = mk_mul(w2), m4 = mk_mul(w4), m128 = mk_mul(w128), m256 = mk_mul(w256), m512 = mk_mul(w512), m1024 = mk_mul(w1024);
  t0[0] = __floats2half2_rn(1.f, 0.f); t0[1] = __floats2half2_rn(w1.r, w1.i); t0[2] = m2.a; t0[4] = m4.a;
  t0[3] = hcm(t0[1], m2); t0[5] = hcm(t0[1], m4); t0[6] = hcm(t0[2], m4); t0[7] = hcm(t0[3], m4);
  put(t0, 0); tile(0, 0);
  t1[0] = m128.a; t2[0] = m256.a; t3[0] = m512.a; t4[0] = m1024.a;
#pragma unroll
  for (int i = 1; i < 8; i++) t1[i] = hcm(t0[i], m128);
  put(t1, 1024); tile(1, 1024);
#pragma unroll
  for (int i = 1; i < 8; i++) t2[i] = hcm((i & 1) ? t1[i & 6] : t0[i & 6], m256);
  put(t2, 0); tile(2, 0);
#pragma unroll
  for (int i = 1; i < 8; i++) t3[i] = hcm((i & 2) ? t2[i & 5] : ((i & 1) ? t1[i & 4] : t0[i & 4]), m512);
  put(t3, 1024); tile(3, 1024);
#pragma unroll
  for (int i = 1; i < 8; i++) t4[i] = hcm((i & 4) ? t3[i & 3] : ((i & 2) ? t2[i & 1] : t1[0]), m1024);
  put(t4, 0); tile(4, 0);
#pragma unroll
  for (int j = 0; j < 5; j++) { k[j][0] *= sc; k[j][1] *= sc; k[j][2] *= sc; k[j][3] *= sc; }
}

__device__ __forceinline__ void build_tables(uint32_t tb, int lane, float (&k)[5][4], float k2048) {
  const int g = lane >> 2, c = lane & 3;
  const uint32_t kc = tb + T_KC + 16;
  {
    const uint32_t a0 = kc + 16 * g + 4 * c, a2 = kc + 2 * (256 + 4 * g + c);
    const uint32_t a3 = kc + 2 * (384 + 2 * g + 64 * (c & 1) + (c >> 1)), a4 = kc + 2 * (512 + g + 32 * c);
#pragma unroll
    for (int r = 0; r < 2; r++) {
      sts32(a0 + 128 * r, pack_bf(k[0][2 * r], k[0][2 * r + 1]));
      sts32(a0 + 128 * r + 256, pack_bf(k[1][2 * r], k[1][2 * r + 1]));
      const uint32_t w2 = pack_bf(k[2][2 * r], k[2][2 * r + 1]);
      const uint32_t w3 = pack_bf(k[3][2 * r], k[3][2 * r + 1]);
      const uint32_t w4 = pack_bf(k[4][2 * r], k[4][2 * r + 1]);
      sts16(a2 + 64 * r, w2); sts16(a2 + 64 * r + 128, w2 >> 16);
      sts16(a3 + 32 * r, w3); sts16(a3 + 32 * r + 64, w3 >> 16);
      sts16(a4 + 16 * r, w4); sts16(a4 + 16 * r + 32, w4 >> 16);
    }
  }
  if (lane == 0) { sts16(kc + 2 * 640, pack_bf(k2048, 0.f)); sts16(kc - 2, 0); }
  __syncwarp();
  const uint32_t td = tb + T_D + 32;
  {
    const uint4 v = lds128(kc + 16 * lane);
    const uint32_t pv = lds16(kc + 16 * lane - 2);
    sts128(td + 32 * lane, __byte_perm(v.x, pv, 0x5410), __byte_perm(v.x, v.x, 0x1032), __byte_perm(v.y, v.x, 0x7610),
           __byte_perm(v.y, v.y, 0x1032));
    sts128(td + 32 * lane + 16, __byte_perm(v.z, v.y, 0x7610), __byte_perm(v.z, v.z, 0x1032),
           __byte_perm(v.w, v.z, 0x7610), __byte_perm(v.w, v.w, 0x1032));
  }
  {
    const uint2 v = lds64(kc + 512 + 8 * lane);
    const uint32_t k4 = lds16(kc + 512 + 8 * lane + 8);
    const uint32_t pv = lds16(kc + (lane == 0 ? 510 : 512 + 8 * lane));
    const uint32_t k22 = __byte_perm(v.y, v.y, 0x1010);
    sts128(td + 1024 + 32 * lane, __byte_perm(v.x, pv, 0x5410), __byte_perm(v.x, v.x, 0x1010),
           __byte_perm(v.x, v.x, 0x1032), __byte_perm(v.y, v.x, 0x7610));
    sts128(td + 1024 + 32 * lane + 16, k22, k22, __byte_perm(v.y, v.y, 0x1032), __byte_perm(k4, v.y, 0x7610));
  }
  {
    const uint32_t kk = lds16(kc + 2 * 384);
    const uint32_t w = lane < 3 ? (kk | (kk << 16)) : (lane == 3 ? (kk << 16) : 0u);
    if (lane < 24) sts32(td + 4 * (lane < 16 ? 512 + lane : lane - 24), w);
    const uint32_t lo_ = lds16(kc + 2 * 511), le_ = lds16(kc + 2 * 512);
    const uint32_t ja = tb + T_5 + (lane < 16 ? 4 * lane : 256 + 4 * lane);
    sts32(ja, lane == 16 ? (le_ << 16) : 0u);
    sts32(ja + 384, lane == 16 ? (lo_ << 16) : 0u);
    sts32(tb + (lane < 16 ? T_7 : T_9 - 64) + 4 * lane, 0u);
  }
#pragma unroll
  for (int s = 0; s < 2; s++) {
    const uint32_t b = kc + 2 * (s ? 512 : 384) + 8 * lane;
    const uint2 v = lds64(b);
    uint32_t em = lds16(b - 2), e0 = v.x;
    const uint32_t e4 = lds16(b + 8);
    if (lane == 0) { em = 0; e0 = 0; }
    sts64(tb + (s ? T_7 : T_3) + 64 + 8 * lane, __byte_perm(v.x, em, 0x5432), __byte_perm(v.y, v.x, 0x7632));
    sts64(tb + (s ? T_9 : T_5) + 64 + 8 * lane, __byte_perm(v.y, e0, 0x5410), __byte_perm(e4, v.y, 0x5410));
  }
  __syncwarp();
}

__device__ __forceinline__ uint32_t box2w(int lo, int n, int o) {
  return ((unsigned)(o - lo) < (unsigned)n ? 0x3F80u : 0u) | ((unsigned)(o + 1 - lo) < (unsigned)n ? 0x3F800000u : 0u);
}

__device__ __forceinline__ void conv_channel(uint32_t ub, uint32_t tb, int lane, uint4* ydst) {
  const int g = lane >> 2, c = lane & 3, x = g - 2 * c;
  const uint32_t st = tb + T_ST + lane * 8;
  const int mi = lane >> 3;
  const uint32_t qa = ub + U_PAD + 16 * (lane & 7) + ((mi == 0 || mi == 3) ? U_ODD : 0) - (mi == 0 ? 16 : 0);
  const uint32_t kv = lds16(tb + T_KC + 16 + 2 * 512);
  {
    const uint32_t hb = ub + U_PAD + (mi & 1) * U_ODD + 16 * ((lane >> 4) + (lane & 7)) - 16;
    const int oh = c < 2 ? 8 + 2 * c : 2 * c - 8;
    const uint32_t bx0 = box2w(g - 4, 9, 2 * c), bx1 = box2w(g - 3, 7, 2 * c), bx2 = box2w(g - 4, 9, oh), bx3 = box2w(g - 3, 7, oh);
    uint32_t f7[9], f9a[9], f9b[9];
    const uint32_t fa = tb + T_7 + 4 * (8 + x);
#pragma unroll
    for (int m = 0; m < 9; m++) {
      f7[m] = lds32(fa + 32 * m);
      f9b[m] = lds32(fa + 320 + 32 * m);
      f9a[m] = lds32(fa + 316 + 32 * m);
    }
    mbar_wait(BAR(MB_EMPTY + 15));
    TS(36);
    uint32_t z09[8], z07[8], zm9[8], zm7[8];
#pragma unroll
    for (int i = 0; i < 8; i++) {
      uint32_t h[4];
      ldsm4(h, hb + 128 * i);
      float y0, y1, y2, y3, w0, w1, w2, w3;
      mma0(y0, y1, y2, y3, bx0, bx1, bx2, bx3, h[2], c < 2 ? h[3] : h[1]);
      mma0(w0, w1, w2, w3, bx0, bx1, bx2, bx3, h[1], c < 2 ? h[2] : h[0]);
      z09[i] = pack_bf(y0, y1); z07[i] = pack_bf(y2, y3);
      zm9[i] = pack_bf(w0, w1); zm7[i] = pack_bf(w2, w3);
    }
    float a[4][2][4];
#pragma unroll
    for (int kap = 0; kap < 4; kap++)
#pragma unroll
      for (int sg = 0; sg < 2; sg++)
#pragma unroll
        for (int bk = 3; bk >= kap; bk--) {
          const int m = 2 * (bk - kap) + 1;
          float(&a0)[4] = a[bk][0];
          float(&a1)[4] = a[bk][1];
          if (sg == 0 && kap == 0) {
            mma0(a0[0], a0[1], a0[2], a0[3], f9a[m], f9a[m + 1], f9a[m - 1], f9a[m], z09[0], z09[1]);
            mma0(a1[0], a1[1], a1[2], a1[3], f9b[m], f9b[m + 1], f9b[m - 1], f9b[m], zm9[0], zm9[1]);
          } else if (sg == 0) {
            mma(a0[0], a0[1], a0[2], a0[3], f9a[m], f9a[m + 1], f9a[m - 1], f9a[m], z09[2 * kap], z09[2 * kap + 1]);
            mma(a1[0], a1[1], a1[2], a1[3], f9b[m], f9b[m + 1], f9b[m - 1], f9b[m], zm9[2 * kap], zm9[2 * kap + 1]);
          } else {
            mma(a0[0], a0[1], a0[2], a0[3], f7[m], f7[m + 1], f7[m - 1], f7[m], zm7[2 * kap], zm7[2 * kap + 1]);
            mma(a1[0], a1[1], a1[2], a1[3], f7[m], f7[m + 1], f7[m - 1], f7[m], z07[2 * kap], z07[2 * kap + 1]);
          }
        }
#pragma unroll
    for (int bk = 0; bk < 4; bk++) {
      sts64(st + 256 * (8 + 2 * bk), pack_bf(a[bk][0][0], a[bk][0][1]), pack_bf(a[bk][1][0], a[bk][1][1]));
      sts64(st + 256 * (9 + 2 * bk), pack_bf(a[bk][0][2], a[bk][0][3]), pack_bf(a[bk][1][2], a[bk][1][3]));
    }
  }
  TS(44);
  {
    const int oh = c < 3 ? 2 * c : -10;
    const uint32_t bx0 = box2w(g - 10, 5, 2 * c - 8), bx1 = box2w(g - 5, 3, 2 * c - 8), bx2 = box2w(g - 10, 5, oh), bx3 = box2w(g - 5, 3, oh);
    const uint32_t lb0 = ((unsigned)(x + 5) < 2u ? kv : 0u) | ((unsigned)(x + 4) < 2u ? kv << 16 : 0u);
    const uint32_t lb1 = ((unsigned)(x - 3) < 2u ? kv : 0u) | ((unsigned)(x - 4) < 2u ? kv << 16 : 0u);
    const int q0 = g - 1, q1 = c < 3 ? g : g - 2;
    uint32_t y0a = ub + U_PAD + (q0 & 1) * U_ODD + 16 * (q0 >> 1) + 4 * c;
    uint32_t y1a = ub + U_PAD + (q1 & 1) * U_ODD + 16 * (q1 >> 1) + 4 * c;
    uint2 a5[10], a3[10];
    const uint32_t aa = tb + T_5 + 4 * (8 + 2 * g - 2 * c);
#pragma unroll
    for (int m = 0; m < 10; m++) { a5[m] = lds64(aa + 32 * m); a3[m] = lds64(aa + 384 + 32 * m); }
    float T[6][4];
#pragma unroll
    for (int i = 0; i < 6; i++) T[i][0] = T[i][1] = T[i][2] = T[i][3] = 0.f;
    uint32_t x5[2] = {0, 0}, x3[2] = {0, 0}, yb[4], lq[4];
    uint32_t lqa = qa, sta = st + 256 * 8;
    uint2 sv;
    auto fetch = [&]() {
      yb[0] = lds32(y0a); yb[1] = lds32(y1a); yb[2] = lds32(y0a + 64); yb[3] = lds32(y1a + 64);
      ldsm4(lq, lqa);
      sv = lds64(min(sta, st + 256 * 15));
      y0a += 128; y1a += 128; lqa += 128; sta += 256;
    };
    fetch();
#pragma unroll 2
    for (int kap = -1; kap < 13; kap++) {
      float yn[2][4];
      mma0(yn[0][0], yn[0][1], yn[0][2], yn[0][3], bx0, bx1, bx2, bx3, yb[0], yb[1]);
      mma0(yn[1][0], yn[1][1], yn[1][2], yn[1][3], bx0, bx1, bx2, bx3, yb[2], yb[3]);
      sts64_p(kap > 0, sta - 256 * 7, pack_bf(T[0][0], T[0][1]), pack_bf(T[0][2], T[0][3]));
#pragma unroll
      for (int i = 0; i < 5; i++)
        mmac_p((unsigned)kap < 12u - i, T[i], a5[2 * i + 1].x, a5[2 * i + 1].y, a5[2 * i].x, a5[2 * i].y, x5[0], x5[1], T[i + 1]);
      const float ci[4] = {bf_lo(sv.x), bf_hi(sv.x), bf_lo(sv.y), bf_hi(sv.y)};
      mmac_p(kap < 7, T[5], lq[0], lq[1], lq[2], lq[3], lb0, lb1, ci);
      fetch();
#pragma unroll
      for (int i = 0; i < 5; i++)
        mma_p((unsigned)kap < 12u - i, T[i], a3[2 * i + 1].x, a3[2 * i + 1].y, a3[2 * i].x, a3[2 * i].y, x3[0], x3[1]);
#pragma unroll
      for (int hh = 0; hh < 2; hh++) { x5[hh] = pack_bf(yn[hh][0], yn[hh][1]); x3[hh] = pack_bf(yn[hh][2], yn[hh][3]); }
    }
  }
  TS(45);
  {
    uint32_t F[66];
    const uint32_t fa = tb + T_D + 32 + 4 * x;
#pragma unroll
    for (int m = 0; m < 66; m++) F[m] = lds32(fa + 32 * m);
    float T[5][4];
#pragma unroll
    for (int i = 0; i < 5; i++) T[i][0] = T[i][1] = T[i][2] = T[i][3] = 0.f;
    uint32_t qd[8][4], held[2] = {0, 0};
    uint32_t qp = qa + 128 * 15, sta = st + 256 * 14;
    uint4* yd = ydst + 19 * 16;
#pragma unroll
    for (int i = 0; i < 6; i++) ldsm4(qd[i], qp - 16 * i);
    uint2 sv = lds64(sta + 256);
    float ci[4] = {bf_lo(sv.x), bf_hi(sv.x), bf_lo(sv.y), bf_hi(sv.y)};
    TS(46);
#pragma unroll 2
    for (int be = 15; be >= 0; be--) {
#pragma unroll
      for (int k = 4; k >= 1; k--)
        mmac_p(be <= 15 - k, T[k], qd[0][0], qd[0][1], qd[0][2], qd[0][3], F[16 * k + 1], F[16 * k], T[k - 1]);
      mmac(T[0], qd[0][0], qd[0][1], qd[0][2], qd[0][3], F[1], F[0], ci);
      ldsm4(qd[6], qp - 16 * 6);
      ldsm4(qd[7], qp - 16 * 7);
      sv = lds64(sta);
#pragma unroll
      for (int i = 1; i < 8; i++) {
#pragma unroll
        for (int k = 3; k >= 0; k--)
          mma_p(k == 0 || be <= 15 - k, T[k], qd[i][0], qd[i][1], qd[i][2], qd[i][3], F[16 * k + 2 * i + 1], F[16 * k + 2 * i]);
        if (i < 7) ldsm4(qd[i - 1], qp - 128 - 16 * (i - 1));
        if (i == 2) {
          const uint32_t w0 = pack_bf(T[4][0], T[4][1]), w1 = pack_bf(T[4][2], T[4][3]);
          st_x_p(be <= 10 && !(be & 1), yd, nz(w0), w1, held[0], held[1]);
          held[0] = w0; held[1] = w1;
        }
        if (i == 4) {
          if (be <= 4) sv = make_uint2(0, 0);
          ci[0] = bf_lo(sv.x); ci[1] = bf_hi(sv.x); ci[2] = bf_lo(sv.y); ci[3] = bf_hi(sv.y);
        }
      }
      qp -= 128; sta -= 256; yd -= 16;
    }
#pragma unroll
    for (int B = 1; B >= 0; B--)
      st_x(ydst + B * 32, nz(pack_bf(T[2 * B][0], T[2 * B][1])), pack_bf(T[2 * B][2], T[2 * B][3]),
           pack_bf(T[2 * B + 1][0], T[2 * B + 1][1]), pack_bf(T[2 * B + 1][2], T[2 * B + 1][3]));
  }
}

__device__ __forceinline__ void dual_exp(const uint32_t* w, uint32_t* e) {
  const float L = 1.44268798828125f;
  uint32_t mx = bmax2(bmax2(w[0], w[1]), bmax2(w[2], w[3]));
  uint32_t mn = bmin2(bmin2(w[0], w[1]), bmin2(w[2], w[3]));
  mx = bmax2(mx, __shfl_xor_sync(0xffffffffu, mx, 1));
  mn = bmin2(mn, __shfl_xor_sync(0xffffffffu, mn, 1));
  mx = bmax2(mx, __shfl_xor_sync(0xffffffffu, mx, 2));
  mn = bmin2(mn, __shfl_xor_sync(0xffffffffu, mn, 2));
  const float mx0 = bf_lo(mx) * -L, mx1 = bf_hi(mx) * -L, mn0 = bf_lo(mn) * L, mn1 = bf_hi(mn) * L;
#pragma unroll
  for (int i = 0; i < 2; i++) {
    const float a0 = bf_lo(w[2 * i]), a1 = bf_hi(w[2 * i]), b0 = bf_lo(w[2 * i + 1]), b1 = bf_hi(w[2 * i + 1]);
    e[2 * i] = pack_bf(ex2(fmaf(a0, L, mx0)), ex2(fmaf(b0, L, mx0)));
    e[2 * i + 1] = pack_bf(ex2(fmaf(a1, L, mx1)), ex2(fmaf(b1, L, mx1)));
    e[4 + 2 * i] = pack_bf(ex2(fmaf(a0, -L, mn0)), ex2(fmaf(b0, -L, mn0)));
    e[5 + 2 * i] = pack_bf(ex2(fmaf(a1, -L, mn1)), ex2(fmaf(b1, -L, mn1)));
  }
}
__device__ __forceinline__ void norm_store(const uint32_t* e, uint32_t dst) {
  float s[4];
  mma0(s[0], s[1], s[2], s[3], e[0], e[1], e[2], e[3], 0x3F803F80u, 0x3F803F80u);
  const uint32_t r = pack_bf(rcp(s[0]), rcp(s[2]));
  const __nv_bfloat162 rr = *(const __nv_bfloat162*)&r;
  uint32_t o[4];
#pragma unroll
  for (int i = 0; i < 4; i++) {
    const __nv_bfloat162 v = __hmul2(*(const __nv_bfloat162*)&e[i], (i & 1) ? __high2bfloat162(rr) : __low2bfloat162(rr));
    o[i] = *(const uint32_t*)&v;
  }
  stsm4(dst, o[0], o[1], o[2], o[3]);
}

__global__ void __launch_bounds__(NTHREADS, 1)
fused_kernel(const Params P, const __grid_constant__ CUtensorMap mx, const __grid_constant__ CUtensorMap mw,
             const __grid_constant__ CUtensorMap mo, const __grid_constant__ CUtensorMap mu,
             const __grid_constant__ CUtensorMap mout) {
  constexpr uint32_t sb = SB;
  const int tid = threadIdx.x, lane = tid & 31;
  const int warp = __shfl_sync(0xffffffffu, tid >> 5, 0);
  const int b = blockIdx.x, oct = b >> 3, i8 = b & 7;
  const int rt = oct < 8 ? oct : 15 - oct;
  const int hp = (oct >> 3) * 8 + i8;

  const int wg = warp >> 2, w = warp & 3;
  const int d = b * 4 + ((tid >> 5) & 3);
  if (tid < 384) {
    asm volatile("prefetch.tensormap [%0];" ::"l"(&mu) : "memory");
    asm volatile("prefetch.tensormap [%0];" ::"l"(&mw) : "memory");
    asm volatile("prefetch.tensormap [%0];" ::"l"(&mx) : "memory");
  }
  if (warp == 12) {
    if (lane == 0) {
#pragma unroll
      for (int i = 0; i < 9; i++) mbar_init(BAR(i), 1);
      asm volatile("fence.mbarrier_init.release.cluster;" ::: "memory");
    }
    __syncwarp();
    if (lane < 9) mbar_expect(BAR(0) + 8 * lane, lane == 0 ? 16384 : 28672);
    __syncwarp();
    e_tma3d(sb + OFF_W, &mw, BAR(MB_FULL), hp * 32, 0, 0);
    e_tma2d(sb + OFF_X + 3 * 16384, &mx, BAR(MB_FULL), 0, rt * 256);
  } else if (warp == 13) {
    if (lane == 0) {
#pragma unroll
      for (int i = 9; i < 39; i++) mbar_init(BAR(i), i < MB_EMPTY ? 1 : (i < MB_AUX ? 4 : 5));
      asm volatile("fence.mbarrier_init.release.cluster;" ::: "memory");
    }
    __syncwarp();
    if (lane < 9) mbar_expect(BAR(MB_FULL + 8) + 8 * lane, lane < 8 ? 16384 : 131072);
  }
  const KgenRaw raw = kgen_load(P, d, tid >> 7, lane);
  const unsigned short dsk = __ldg((const unsigned short*)P.Dskip + d);
  if (warp == 12) {
#pragma unroll 1
    for (int kb = 1; kb < 4; kb++) {
      e_tma3d(sb + OFF_W + kb * 12288, &mw, BAR(MB_FULL) + 8 * kb, hp * 32, kb * 64, 0);
      e_tma2d(sb + OFF_X + (kb < 2 ? kb + 3 : kb - 2) * 16384, &mx, BAR(MB_FULL) + 8 * kb, kb * 64, rt * 256);
    }
    e_tma5d(sb + OFF_STG0, &mu, BAR(MB_URAW), i8 * 64, oct * 4);
    e_prefetch(P.x + (size_t)(rt * 256 + hp * 16) * 512, 16384);
    e_prefetch(P.wqkv + (size_t)(256 + b * 2) * 1536, 6144);
    if (smem_u32(smem_raw) != SB) __trap();
    if (lane == 0) TS1(54);
  }
  const uint32_t tb = sb + OFF_T + w * T_CH;
  float k[5][4], k2048;
  {
    const uint32_t kp = wg == 3 ? sb + OFF_X + 32768 + w * 4096 : tb + (wg & 1) * 2608;
    kgen_unit(raw, lane, wg == 2 ? sb + OFF_STG0 + 16384 + w * 2048 : (kp + 127) & ~127u, k, k2048);
    TS(40 + wg);
    k2048 += __shfl_xor_sync(0xffffffffu, k2048, 16);
    k2048 += __shfl_xor_sync(0xffffffffu, k2048, 8);
    if (wg != 2 || (fu(k[0][0]) & fu(k[1][0]) & fu(k[2][0]) & fu(k[3][0]) & fu(k[4][0])) == 0xffffffffu) {
#pragma unroll
      for (int j = 0; j < 5; j++) sts128(kp + j * 512 + lane * 16, fu(k[j][0]), fu(k[j][1]), fu(k[j][2]), fu(k[j][3]));
      if (lane < 8) sts32(kp + 2560 + lane * 4, fu(k2048));
    }
  }
  __syncthreads();
  if (warp >= 12) {
    asm volatile("setmaxnreg.dec.sync.aligned.u32 32;");
    if (warp == 12) {
#pragma unroll 1
      for (int kb = 4; kb < 8; kb++) {
        e_tma3d(sb + OFF_W + kb * 12288, &mw, BAR(MB_FULL) + 8 * kb, hp * 32, kb * 64, 0);
        if (kb == 4) {
          nb_sync(NB_KREAD, 160);
          asm volatile("fence.proxy.async.shared::cta;" ::: "memory");
          e_tma2d(sb + OFF_X + 2 * 16384, &mx, BAR(MB_FULL + 4), 256, rt * 256);
        }
      }
      uint32_t slot = sb + OFF_X + 3 * 16384;
#pragma unroll 1
      for (int n = 0; n < 11; n++) {
        mbar_wait(BAR(MB_EMPTY) + 8 * n);
        const int m = n + 5;
        e_tma2d(slot, &mx, BAR(MB_FULL) + 8 * m, (m & 7) * 64, rt * 256 + (m >> 3) * 128);
        slot = slot == sb + OFF_X + 4 * 16384 ? sb + OFF_X : slot + 16384;
        if (n == 7) e_prefetch(P.wo + (size_t)b * 2048, 4096);
      }
#pragma unroll 1
      for (int i = 0; i < 8; i++) {
        mbar_wait(BAR(MB_EMPTY + 10) + 8 * ((0x54332100u >> (4 * i)) & 7));
        const int w0 = (0x54736210u >> (4 * i)) & 7;
        e_tma3d(sb + OFF_W + w0 * 16384, &mo, BAR(MB_WO), 0, w0 * 64, (hp & 3) * 2);
      }
    } else {
      if (warp == 15) {
        const uint4 v0 = __ldg((const uint4*)P.wphi + hp * 64 + lane), v1 = __ldg((const uint4*)P.wphi + hp * 64 + 32 + lane);
        sts128(sb + OFF_PHI + (lane & 1) * 256 + (lane >> 1) * 16, v0.x, v0.y, v0.z, v0.w);
        sts128(sb + OFF_PHI + 512 + (lane & 1) * 256 + (lane >> 1) * 16, v1.x, v1.y, v1.z, v1.w);
        asm volatile("fence.proxy.async.shared::cta;" ::: "memory");
        __syncwarp();
        if (lane == 0) mbar_arrive(BAR(MB_AUX));
        mbar_wait(BAR(MB_EMPTY + ZERO_STEP));
        uint4* py = P.xs + X_Y + b * 1024 + lane;
#pragma unroll 1
        for (int i = 0; i < 1024; i += 32) st_x(py + i, 0, 0, 0, 0);
        nb_arrive(NB_YZ, 160);
        nb_arrive(NB_ODONE, 320);
        if (lane == 0) TS1(55);
        return;
      }
      uint32_t* const cnt = (uint32_t*)(P.xs + X_CNT) + (warp == 13 ? i8 : 8 + rt) * 32;
      const unsigned target = (ld_x32(cnt) & ~15u) + 16;
      if (warp == 13) {
        uint4* pp = P.xs + X_PART + (hp * 8 + rt) * 144 + lane;
#pragma unroll 1
        for (int i = 0; i < 144; i += 32) if (i + lane < 144) st_x(pp + i, 0, 0, 0, 0);
      }
      nb_sync(warp == 13 ? NB_INIT : NB_ODONE, warp == 13 ? 160 : 320);
      if (lane == 0) TS1(warp == 13 ? 49 : 56);
      asm volatile("fence.proxy.async.shared::cta;" ::: "memory");
      if (lane == 0) asm volatile("red.release.gpu.global.add.u32 [%0], 1;" ::"l"(cnt) : "memory");
      if (lane == 0) TS1(warp == 13 ? 50 : 57);
      const uint32_t* pc = (warp == 13 && (lane & 1)) ? (uint32_t*)(P.xs + X_CNT) + (b >> 4) * 32 : cnt;
#pragma unroll 1
      for (int i = 0; i < SPIN_MAX; i++) {
        unsigned v;
        asm volatile("ld.acquire.gpu.global.u32 %0, [%1];" : "=r"(v) : "l"(pc) : "memory");
        if (__all_sync(0xffffffffu, (int)(v - target) >= 0)) break;
      }
      if (lane == 0) TS1(warp == 13 ? 51 : 58);
      asm volatile("fence.proxy.async.global;" ::: "memory");
      if (warp == 13) {
        mbar_wait(BAR(MB_EMPTY + 11));
        e_expect(BAR(MB_UFULL), 4 * U_CH);
        e_bulk(sb + OFF_U, P.xs + X_UT + b * (U_CH / 4), 4 * U_CH, BAR(MB_UFULL));
      } else {
        const uint4* src = P.xs + X_O + (rt * 4 + (hp >> 2)) * 4096;
        e_expect(BAR(MB_OA), 14336);
        e_bulk(sb + OFF_STG0, src + 3200, 14336, BAR(MB_OA));
        e_expect(BAR(MB_OC), 32768);
        e_bulk(sb + OFF_X + 32768, src, 32768, BAR(MB_OC));
        nb_sync(NB_BDONE, 288);
        asm volatile("fence.proxy.async.shared::cta;" ::: "memory");
        e_expect(BAR(MB_OB), 18432);
        e_bulk(sb + OFF_U, src + 2048, 18432, BAR(MB_OB));
      }
    }
    return;
  }

  asm volatile("setmaxnreg.inc.sync.aligned.u32 160;");
  const int t = tid & 127;
  const int g = lane >> 2, c = lane & 3;
  {
    if (wg == 2) {
#pragma unroll 1
      for (int q = 0; q < 3; q++) {
        const uint32_t src = q ? tb + (q - 1) * 2608 : sb + OFF_X + 32768 + w * 4096;
#pragma unroll
        for (int j = 0; j < 5; j++) {
          const uint4 v = lds128(src + j * 512 + lane * 16);
          k[j][0] += uf(v.x); k[j][1] += uf(v.y); k[j][2] += uf(v.z); k[j][3] += uf(v.w);
        }
        k2048 += uf(lds32(src + 2560 + (lane & 7) * 4));
        if (q == 0) nb_arrive(NB_KREAD, 160);
      }
#pragma unroll
      for (int o2 = 4; o2; o2 >>= 1) k2048 += __shfl_xor_sync(0xffffffffu, k2048, o2);
      if (lane == 0) k[0][0] += bf_lo(dsk);
      __syncwarp();
      TS(34);
      build_tables(tb, lane, k, k2048);
      TS(35);
      nb_sync(NB_YZ, 160);
      mbar_wait(BAR(MB_UFULL));
      uint4* const g_y = P.xs + X_Y;
      conv_channel(sb + OFF_U + w * U_CH, tb, lane, g_y + (size_t)d * 256 + lane);
      nb_arrive(NB_BDONE, 288);
      TS(37);
      mbar_wait(BAR(MB_OA));
      const int lam = w * 8 + g;
      const uint4* src = g_y + (size_t)(oct * 32 + c * 8) * 256 + i8 * 32 + lam;
      uint4 v[8];
#pragma unroll 1
      for (int it = 0; it < SPIN_MAX; it++) {
        uint32_t m = 0xffffffffu;
#pragma unroll
        for (int i = 0; i < 8; i++) v[i] = ld_x(src + i * 256);
#pragma unroll
        for (int i = 0; i < 8; i++) m = min(m, v[i].x);
        if (__all_sync(0xffffffffu, m != 0)) break;
      }
      __nv_bfloat16* dst = P.out + (size_t)(i8 * 256 + (lam >> 2) * 16 + (lam & 3) * 2) * 1024 + 512 + oct * 32 + c * 8;
#pragma unroll
      for (int i = 0; i < 8; i++) *(uint4*)(dst + (size_t)((i >> 2) * 128 + ((i >> 1) & 1) * 8 + (i & 1)) * 1024) = tr_row(v, i);
      TS(38);
      GT(63);
      return;
    }
    if (wg == 1) {
      mbar_wait(BAR(MB_URAW));
      TS(48);
      uint4* dst = P.xs + X_UT + (i8 * 64 + g) * (U_CH / 16) + (c & 1) * (U_ODD / 16) + U_PAD / 16 + oct * 8 + w * 2 + (c >> 1);
      uint32_t r[8][4];
#pragma unroll
      for (int i = 0; i < 8; i++) ldsm4t(r[i], sb + OFF_STG0 + w * 4096 + lane * 128 + (((i ^ lane) & 7) << 4));
#pragma unroll
      for (int i = 0; i < 8; i++) dst[i * (U_CH / 2)] = make_uint4(r[i][0], r[i][1], r[i][2], r[i][3]);
      nb_arrive(NB_INIT, 160);
      if (lane == 0) mbar_arrive(BAR(MB_AUX));
      mbar_wait(BAR(MB_EMPTY + 6));
    }
    TS(wg * 16 + 1);
  }

  float acc[2][48];
  {
    uint32_t fb = BAR(MB_FULL) + 64 * wg;
    uint32_t da = (uint32_t)mkdesc(sb + OFF_X, 16, 0, 0) + (wg ? 1024 : 3072), db = (uint32_t)mkdesc(sb + OFF_W, 4096, 0, 0);
    constexpr uint64_t ha = mkdesc(0, 0, 1024, 1), hb = mkdesc(0, 0, 512, 2);
#pragma unroll 1
    for (int kb = 0; kb < 8; kb++) {
      mbar_wait(fb);
      if (kb == 0) TS(wg * 16 + 2);
      WG_FENCE();
#pragma unroll
      for (int k = 0; k < 4; k++) {
        wgmma_ss_n96(acc[0], ha | (da + 2 * k), hb | (db + 64 * k), k ? 1 : kb);
        wgmma_ss_n96(acc[1], ha | (da + 2 * k + 512), hb | (db + 64 * k), k ? 1 : kb);
      }
      WG_COMMIT();
      WG_WAIT(1);
      if (kb > 0 && lane == 0) mbar_arrive(fb + 8 * (MB_EMPTY - MB_FULL - 1));
      fb += 8; db += 768;
      da = da == (uint32_t)mkdesc(sb + OFF_X + 65536, 16, 0, 0) ? da - 4096 : da + 1024;
    }
    WG_WAIT(0);
    if (lane == 0) mbar_arrive(fb + 8 * (MB_EMPTY - MB_FULL - 1));
    mbar_wait(fb + 8 * (MB_EMPTY - MB_FULL - 1));
  }
  TS(wg * 16 + 3);

  constexpr uint32_t stg0 = sb + OFF_STG0, stg1 = sb + OFF_X + 32768;
  const uint32_t sl = (wg ? stg1 : stg0) + w * 3072 + lane * 16;
  uint32_t pw[32], eq[32];
  {
    uint4 af[8];
#pragma unroll
    for (int u = 0; u < 8; u++) {
      const float* a = acc[(u >> 1) & 1] + (u < 4 ? 16 : 0) + 8 * (u & 1);
      af[u] = make_uint4(pack_bf(a[0], a[1]), pack_bf(a[2], a[3]), pack_bf(a[4], a[5]), pack_bf(a[6], a[7]));
    }
    mbar_wait(BAR(MB_AUX));
    float p[8][8];
    WG_FENCE();
#pragma unroll
    for (int u = 0; u < 8; u++) wgmma_rs_n16(p[u], af[u], mkdesc(sb + OFF_PHI + (u & 1) * 512, 128, 256, 0), 0);
    WG_COMMIT();
#pragma unroll
    for (int i = 0; i < 4; i++) {
      const float* a = acc[i >> 1] + 32 + 8 * (i & 1);
      stsm4(sl + (i >> 1) * 12288 + 2048 + (i & 1) * 512, pack_bf(a[0], a[1]), pack_bf(a[2], a[3]), pack_bf(a[4], a[5]), pack_bf(a[6], a[7]));
    }
    WG_WAIT(0);
#pragma unroll
    for (int u = 0; u < 8; u++) {
      pw[4 * u] = pack_bf(p[u][0], p[u][2]); pw[4 * u + 1] = pack_bf(p[u][1], p[u][3]);
      pw[4 * u + 2] = pack_bf(p[u][4], p[u][6]); pw[4 * u + 3] = pack_bf(p[u][5], p[u][7]);
    }
  }
  uint32_t ek[32];
  if (wg == 0) {
#pragma unroll
    for (int i = 0; i < 16; i++) { const uint32_t x = pw[i]; pw[i] = pw[16 + i]; pw[16 + i] = x; }
  }
#pragma unroll 1
  for (int it = 0; it < 2; it++) {
#pragma unroll
    for (int i = 0; i < 32; i++) ek[i] = eq[i];
#pragma unroll
    for (int u = 0; u < 4; u++) dual_exp(pw + 4 * u, eq + 8 * u);
    if (it != wg) {
      TS(wg * 16 + 12);
      mbar_wait(BAR(MB_EMPTY + 15));
#pragma unroll
      for (int i = 0; i < 8; i++) norm_store(eq + 4 * i, sl + (i >> 2) * 12288 + (i & 3) * 512);
      if (wg) nb_arrive(NB_ST0, 256);
    }
#pragma unroll
    for (int i = 0; i < 16; i++) pw[i] = pw[i + 16];
  }
  TS(wg * 16 + 4);
  uint4* const g_part = P.xs + X_PART;
  uint4* const g_o = P.xs + X_O;
  const uint32_t kvs = stg0;
  if (wg == 0) {
#pragma unroll
    for (int i = 0; i < 32; i++) eq[i] = ek[i];
    nb_sync(NB_WG0, 128);
    mbar_wait(BAR(MB_UFULL));
    float kv[12], kw[12];
#pragma unroll
    for (int i = 0; i < 12; i++) kv[i] = kw[i] = 0.f;
    const int mi = lane >> 3;
    const uint32_t ao = w * 512 + (lane & 7) * 16 + ((mi & 1) * 2 + (mi >> 1)) * 128, bo = 2048 + (w >> 1) * 512 + lane * 16;
#pragma unroll 1
    for (int j = 0; j < 2; j++) {
      if (j) nb_sync(NB_ST0, 256);
      const uint32_t sg = j ? stg1 : stg0;
      uint32_t a[8][4], bb[8][4];
#pragma unroll
      for (int s = 0; s < 8; s++) { ldsm4t(a[s], sg + s * 3072 + ao); ldsm4t(bb[s], sg + s * 3072 + bo); }
#pragma unroll
      for (int s = 0; s < 8; s++) {
        float* o = (s & 1) ? kw : kv;
        mma(o[0], o[1], o[2], o[3], a[s][0], a[s][1], a[s][2], a[s][3], bb[s][0], bb[s][1]);
        mma(o[4], o[5], o[6], o[7], a[s][0], a[s][1], a[s][2], a[s][3], bb[s][2], bb[s][3]);
        mma(o[8], o[9], o[10], o[11], a[s][0], a[s][1], a[s][2], a[s][3], 0x3F803F80u, 0x3F803F80u);
      }
    }
#pragma unroll
    for (int i = 0; i < 12; i++) kv[i] += kw[i];
    uint4* pp = g_part + (size_t)(hp * 8 + rt) * 144;
    st_x(pp + t, nz(pack_bf(kv[0], kv[1])), pack_bf(kv[2], kv[3]), pack_bf(kv[4], kv[5]), pack_bf(kv[6], kv[7]));
    if (c < 2) st_x32((uint32_t*)(pp + 128) + w * 16 + c * 8 + g, nz(fu(c ? kv[10] : kv[8])));
    TS(5);
    const uint4* ps = g_part + (size_t)hp * 8 * 144 + t;
    const uint32_t* zs = (const uint32_t*)(g_part + (size_t)(hp * 8 + (lane >> 4) * 4) * 144 + 128) + w * 16 + (lane & 15);
    uint4 v[8];
    uint32_t zv[4];
#pragma unroll 1
    for (int it = 0; it < SPIN_MAX; it++) {
#pragma unroll
      for (int i = 0; i < 8; i++) v[i] = ld_x(ps + i * 144);
#pragma unroll
      for (int i = 0; i < 4; i++) zv[i] = ld_x32(zs + i * 576);
      uint32_t m = min(min(zv[0], zv[1]), min(zv[2], zv[3]));
#pragma unroll
      for (int i = 0; i < 8; i++) m = min(m, v[i].x);
      if (__all_sync(0xffffffffu, m != 0)) break;
    }
    float s4[4][4];
#pragma unroll
    for (int i = 0; i < 4; i++) s4[i][0] = s4[i][1] = s4[i][2] = s4[i][3] = 0.f;
    const uint32_t eye = (g >> 1) == c ? ((g & 1) ? 0x3F800000u : 0x3F80u) : 0u;
#pragma unroll
    for (int r = 0; r < 8; r++) {
      mma_k8(s4[(r & 1) * 2], v[r].x, v[r].y, eye);
      mma_k8(s4[(r & 1) * 2 + 1], v[r].z, v[r].w, eye);
    }
    float s[8];
#pragma unroll
    for (int i = 0; i < 8; i++) s[i] = s4[i >> 2][i & 3] + s4[2 + (i >> 2)][i & 3];
    float zsum = (uf(zv[0]) + uf(zv[1])) + (uf(zv[2]) + uf(zv[3]));
    zsum += __shfl_xor_sync(0xffffffffu, zsum, 16);
    stsm4(kvs + w * 512 + lane * 16, pack_bf(s[0], s[1]), pack_bf(s[2], s[3]), pack_bf(s[4], s[5]), pack_bf(s[6], s[7]));
    sts16(kvs + 2048 + (lane >> 4) * 128 + (w * 16 + (lane & 15)) * 2, lane < 16 ? pack_bf(zsum, 0.f) : 0x3F80u);
    TS(6);
  }
  nb_sync(NB_KV, 256);
  {
    uint32_t kb_[4][4], zb[8];
#pragma unroll
    for (int i = 0; i < 4; i++) ldsm4t(kb_[i], kvs + i * 512 + lane * 16);
#pragma unroll
    for (int i = 0; i < 8; i++) zb[i] = lds32(kvs + 2048 + (g & 1) * 128 + i * 16 + c * 4);
    uint32_t* od = (uint32_t*)(g_o + (size_t)((rt * 4 + wg * 2) * 32 + hp * 2) * 128) + w * 64 + lane;
#pragma unroll
    for (int mt = 0; mt < 2; mt++) {
#pragma unroll
      for (int h = 0; h < 2; h++) {
        const uint32_t* e = eq + 16 * mt + 8 * h;
        float n[8], nm[8], dp[4], dm[4];
        mma0(dp[0], dp[1], dp[2], dp[3], e[0], e[1], e[2], e[3], zb[4 * h], zb[4 * h + 1]);
        mma0(dm[0], dm[1], dm[2], dm[3], e[4], e[5], e[6], e[7], zb[4 * h + 2], zb[4 * h + 3]);
        mma0(n[0], n[1], n[2], n[3], e[0], e[1], e[2], e[3], kb_[2 * h][0], kb_[2 * h][1]);
        mma0(nm[0], nm[1], nm[2], nm[3], e[4], e[5], e[6], e[7], kb_[2 * h + 1][0], kb_[2 * h + 1][1]);
        mma0(n[4], n[5], n[6], n[7], e[0], e[1], e[2], e[3], kb_[2 * h][2], kb_[2 * h][3]);
        mma0(nm[4], nm[5], nm[6], nm[7], e[4], e[5], e[6], e[7], kb_[2 * h + 1][2], kb_[2 * h + 1][3]);
        const float q0 = dp[1] * rcp(dm[1]), q1 = dp[3] * rcp(dm[3]);
        const float r0 = rcp(fmaf(dm[0], q0, fmaf(dp[1], 1e-6f, dp[0]))), r1 = rcp(fmaf(dm[2], q1, fmaf(dp[3], 1e-6f, dp[2])));
#pragma unroll
        for (int i = 0; i < 8; i++) n[i] = fmaf(nm[i], (i & 2) ? q1 : q0, n[i]);
        od[h * 512] = pack_bf(n[0] * r0, n[1] * r0);
        od[h * 512 + 32] = pack_bf(n[2] * r1, n[3] * r1);
        od[h * 512 + 256] = pack_bf(n[4] * r0, n[5] * r0);
        od[h * 512 + 288] = pack_bf(n[6] * r1, n[7] * r1);
      }
      od += 16384;
    }
  }
  TS(wg * 16 + 7);
  nb_arrive(NB_ODONE, 320);
  if (wg) return;
  mbar_wait(BAR(MB_WO));
  mbar_wait(BAR(MB_OA));
  TS(8);
  nb_sync(NB_BDONE, 288);
  TS(9);
  float oc[64];
  {
    constexpr uint64_t ha = mkdesc(0, 0, 128, 0), hb = mkdesc(0, 0, 1024, 1);
    constexpr uint32_t da0 = (uint32_t)mkdesc(stg1, 1024, 0, 0), db0 = (uint32_t)mkdesc(sb + OFF_W, 8192, 0, 0);
#pragma unroll 1
    for (int j = 0; j < 8; j++) {
      const int kb = (j + 7) & 7;
      if ((j & 3) == 1) mbar_wait(j == 1 ? BAR(MB_OC) : BAR(MB_OB));
      WG_FENCE();
#pragma unroll
      for (int k = 0; k < 4; k++) wgmma_ss_n128(oc, ha | (da0 + 512 * kb + 128 * k), hb | (db0 + 1024 * kb + 128 * k), k ? 1 : j);
      WG_COMMIT();
    }
    WG_WAIT(0);
  }
  TS(10);
  nb_sync(NB_WG0, 128);
  const uint32_t ot = sb + OFF_W + w * 4096;
#pragma unroll
  for (int i = 0; i < 16; i += 2)
    stsm4(ot + (i >> 3) * 2048 + (lane & 15) * 128 + (((i + (lane >> 4)) ^ lane) & 7) * 16, pack_bf(oc[4 * i], oc[4 * i + 1]),
          pack_bf(oc[4 * i + 2], oc[4 * i + 3]), pack_bf(oc[4 * i + 4], oc[4 * i + 5]), pack_bf(oc[4 * i + 6], oc[4 * i + 7]));
  asm volatile("fence.proxy.async.shared::cta;" ::: "memory");
  __syncwarp();
  e_store3d(&mout, ot, (rt * 4 + (hp >> 2)) * 64 + w * 16, (hp & 3) * 2);
  TS(wg * 16 + 11);
  GT(61 + wg);
}

typedef CUresult (*EncodeFn)(CUtensorMap*, CUtensorMapDataType, cuuint32_t, void*, const cuuint64_t*, const cuuint64_t*,
                             const cuuint32_t*, const cuuint32_t*, CUtensorMapInterleave, CUtensorMapSwizzle,
                             CUtensorMapL2promotion, CUtensorMapFloatOOBfill);

}

extern "C" void kernel_launch(void* const* d_in, const int* in_sizes, int n_in, void* d_out, int out_size) {
  (void)in_sizes; (void)n_in; (void)out_size;
  void* fn = nullptr;
  cudaDriverEntryPointQueryResult qr;
  cudaGetDriverEntryPoint("cuTensorMapEncodeTiled", &fn, cudaEnableDefault, &qr);
  EncodeFn enc = (EncodeFn)fn;
  CUtensorMap mx, mw, mo, mu, mout;
  const cuuint32_t es[5] = {1, 1, 1, 1, 1};
  {
    cuuint64_t dims[2] = {512, 2048}, st[1] = {1024};
    cuuint32_t box[2] = {64, 128};
    enc(&mx, CU_TENSOR_MAP_DATA_TYPE_BFLOAT16, 2, d_in[0], dims, st, box, es, CU_TENSOR_MAP_INTERLEAVE_NONE,
        CU_TENSOR_MAP_SWIZZLE_128B, CU_TENSOR_MAP_L2_PROMOTION_L2_128B, CU_TENSOR_MAP_FLOAT_OOB_FILL_NONE);
  }
  {
    cuuint64_t dims[3] = {512, 512, 3}, st[2] = {3072, 1024};
    cuuint32_t box[3] = {32, 64, 3};
    enc(&mw, CU_TENSOR_MAP_DATA_TYPE_BFLOAT16, 3, d_in[1], dims, st, box, es, CU_TENSOR_MAP_INTERLEAVE_NONE,
        CU_TENSOR_MAP_SWIZZLE_64B, CU_TENSOR_MAP_L2_PROMOTION_L2_128B, CU_TENSOR_MAP_FLOAT_OOB_FILL_NONE);
  }
  {
    cuuint64_t dims[3] = {64, 512, 8}, st[2] = {1024, 128};
    cuuint32_t box[3] = {64, 64, 2};
    enc(&mo, CU_TENSOR_MAP_DATA_TYPE_BFLOAT16, 3, d_in[3], dims, st, box, es, CU_TENSOR_MAP_INTERLEAVE_NONE,
        CU_TENSOR_MAP_SWIZZLE_128B, CU_TENSOR_MAP_L2_PROMOTION_L2_128B, CU_TENSOR_MAP_FLOAT_OOB_FILL_NONE);
  }
  {
    cuuint64_t dims[5] = {512, 2, 4, 4, 64}, st[4] = {1024, 8192, 2048, 32768};
    cuuint32_t box[5] = {64, 2, 4, 4, 4};
    enc(&mu, CU_TENSOR_MAP_DATA_TYPE_BFLOAT16, 5, d_in[4], dims, st, box, es, CU_TENSOR_MAP_INTERLEAVE_NONE,
        CU_TENSOR_MAP_SWIZZLE_128B, CU_TENSOR_MAP_L2_PROMOTION_L2_128B, CU_TENSOR_MAP_FLOAT_OOB_FILL_NONE);
  }
  {
    cuuint64_t dims[3] = {64, 2048, 16}, st[2] = {2048, 128};
    cuuint32_t box[3] = {64, 16, 2};
    enc(&mout, CU_TENSOR_MAP_DATA_TYPE_BFLOAT16, 3, d_out, dims, st, box, es, CU_TENSOR_MAP_INTERLEAVE_NONE,
        CU_TENSOR_MAP_SWIZZLE_128B, CU_TENSOR_MAP_L2_PROMOTION_NONE, CU_TENSOR_MAP_FLOAT_OOB_FILL_NONE);
  }
  Params P;
  P.x = (const __nv_bfloat16*)d_in[0];
  P.wqkv = (const __nv_bfloat16*)d_in[1];
  P.wphi = (const __nv_bfloat16*)d_in[2];
  P.wo = (const __nv_bfloat16*)d_in[3];
  P.logA = (const __nv_bfloat16*)d_in[5];
  P.Aim = (const __nv_bfloat16*)d_in[6];
  P.Cre = (const __nv_bfloat16*)d_in[7];
  P.Cim = (const __nv_bfloat16*)d_in[8];
  P.logdt = (const __nv_bfloat16*)d_in[9];
  P.Dskip = (const __nv_bfloat16*)d_in[10];
  P.out = (__nv_bfloat16*)d_out;
  cudaGetSymbolAddress((void**)&P.xs, g_x);
  P.ts = nullptr;
  cudaFuncSetAttribute(fused_kernel, cudaFuncAttributeMaxDynamicSharedMemorySize, SMEM_BYTES);
  fused_kernel<<<NCTA, NTHREADS, SMEM_BYTES>>>(P, mx, mw, mo, mu, mout);
}
```

```cpp
#include <cuda_runtime.h>
#include <cuda_bf16.h>
#include <cuda_fp16.h>
#include <cuda.h>
#include <stdint.h>

#define DBG_TS 0

namespace {

constexpr int NTHREADS = 512;
constexpr int NCTA = 128;
constexpr int OFF_W = 0;
constexpr int OFF_X = 98304;
constexpr int OFF_U = OFF_X + 65536;
constexpr int U_CH = 4416, U_ODD = 2240, U_PAD = 128;
constexpr int OFF_STG0 = OFF_U + 18432;
constexpr int OFF_T = OFF_STG0 + 24576;
constexpr int T_CH = 5216;
constexpr int T_D = 0;
constexpr int T_5 = 2144;
constexpr int T_3 = T_5 + 384;
constexpr int T_7 = T_5 + 1024;
constexpr int T_9 = T_7 + 320;
constexpr int T_KC = T_9 + 320;
constexpr int T_ST = T_5 - 1024;
constexpr int OFF_PHI = OFF_T + 4 * T_CH;
constexpr int OFF_BAR = OFF_PHI + 1024;
constexpr int SMEM_BYTES = OFF_BAR + 512;
constexpr uint32_t SB = 1024;
static_assert(T_KC + 2 * 656 <= T_CH, "table size");
static_assert(SMEM_BYTES <= 232448, "smem");
constexpr int MB_URAW = 0, MB_FULL = 1  , MB_WO = 17, MB_UFULL = 18, MB_OA = 19, MB_OB = 20, MB_OC = 21,
              MB_EMPTY = 22  , MB_AUX = 38;
__host__ __device__ constexpr uint32_t BAR(int i) { return SB + OFF_BAR + 8 * i; }
constexpr int NB_WG0 = 1, NB_ODONE = 2, NB_ST0 = 3  , NB_KV = 5, NB_YZ = 6, NB_INIT = 7, NB_PREP = 8, NB_PROD = 9, NB_KREAD = 10, NB_BDONE = 11, NB_ZERO = 12;
#define ZERO_STEP 7
constexpr int SPIN_MAX = 1 << 16;

constexpr int X_CNT = 0;
constexpr int X_PART = 128;
constexpr int X_O = X_PART + 16 * 8 * 144;
constexpr int X_Y = X_O + 32 * 32 * 128;
constexpr int X_UT = X_Y + 512 * 8 * 32;
constexpr int X_SIZE = X_UT + 512 * (U_CH / 16);
__device__ __align__(128) uint4 g_x[X_SIZE];
extern __shared__ uint8_t smem_raw[];
#define TS(i) do {} while (0)
#define TS1(i) do {} while (0)
#define GT(i) do {} while (0)

__device__ __forceinline__ uint32_t smem_u32(const void* p) { return (uint32_t)__cvta_generic_to_shared(p); }
__device__ __forceinline__ void mbar_arrive(uint32_t b) {
  asm volatile("mbarrier.arrive.shared::cta.b64 _, [%0];" ::"r"(b) : "memory");
}
__device__ __forceinline__ void mbar_wait(uint32_t b) {
  uint32_t done = 0;
#pragma unroll 1
  for (int i = 0; i < SPIN_MAX && !done; i++) {
    asm volatile("{\n.reg .pred p;\nmbarrier.try_wait.parity.shared::cta.b64 p, [%1], 0, 4000;\nselp.u32 %0, 1, 0, p;\n}\n"
                 : "=r"(done) : "r"(b) : "memory");
  }
}
__device__ __forceinline__ void mbar_init(uint32_t b, int n) {
  asm volatile("mbarrier.init.shared::cta.b64 [%0], %1;" ::"r"(b), "r"(n) : "memory");
}
__device__ __forceinline__ void mbar_expect(uint32_t b, int bytes) {
  asm volatile("mbarrier.arrive.expect_tx.shared::cta.b64 _, [%0], %1;" ::"r"(b), "r"(bytes) : "memory");
}
__device__ __forceinline__ void nb_sync(int id, int n) { asm volatile("bar.sync %0, %1;" ::"r"(id), "r"(n) : "memory"); }
__device__ __forceinline__ void nb_arrive(int id, int n) { asm volatile("bar.arrive %0, %1;" ::"r"(id), "r"(n) : "memory"); }
#define ELECT "{\n.reg .pred p;\nelect.sync _|p, 0xffffffff;\n@p "
__device__ __forceinline__ void e_expect(uint32_t b, int bytes) {
  asm volatile(ELECT "mbarrier.arrive.expect_tx.shared::cta.b64 _, [%0], %1;\n}\n" ::"r"(b), "r"(bytes) : "memory");
}
__device__ __forceinline__ void e_tma2d(uint32_t dst, const CUtensorMap* m, uint32_t bar, int c0, int c1) {
  asm volatile(ELECT "cp.async.bulk.tensor.2d.shared::cluster.global.mbarrier::complete_tx::bytes [%0], [%1, {%3,%4}], [%2];\n}\n"
               ::"r"(dst), "l"(m), "r"(bar), "r"(c0), "r"(c1) : "memory");
}
__device__ __forceinline__ void e_tma3d(uint32_t dst, const CUtensorMap* m, uint32_t bar, int c0, int c1, int c2) {
  asm volatile(ELECT "cp.async.bulk.tensor.3d.shared::cluster.global.mbarrier::complete_tx::bytes [%0], [%1, {%3,%4,%5}], [%2];\n}\n"
               ::"r"(dst), "l"(m), "r"(bar), "r"(c0), "r"(c1), "r"(c2) : "memory");
}
__device__ __forceinline__ void e_tma4d(uint32_t dst, const CUtensorMap* m, uint32_t bar, int c0, int c3) {
  asm volatile(ELECT "cp.async.bulk.tensor.4d.shared::cluster.global.mbarrier::complete_tx::bytes [%0], [%1, {%3,%5,%5,%4}], [%2];\n}\n"
               ::"r"(dst), "l"(m), "r"(bar), "r"(c0), "r"(c3), "r"(0) : "memory");
}
__device__ __forceinline__ void e_tma5d(uint32_t dst, const CUtensorMap* m, uint32_t bar, int c0, int c4) {
  asm volatile(ELECT "cp.async.bulk.tensor.5d.shared::cluster.global.mbarrier::complete_tx::bytes [%0], [%1, {%3,%5,%5,%5,%4}], [%2];\n}\n"
               ::"r"(dst), "l"(m), "r"(bar), "r"(c0), "r"(c4), "r"(0) : "memory");
}
__device__ __forceinline__ void e_bulk(uint32_t dst, const void* src, int bytes, uint32_t bar) {
  asm volatile(ELECT "cp.async.bulk.shared::cluster.global.mbarrier::complete_tx::bytes [%0], [%1], %2, [%3];\n}\n"
               ::"r"(dst), "l"(src), "r"(bytes), "r"(bar) : "memory");
}
__device__ __forceinline__ void e_prefetch(const void* p, int bytes) {
  asm volatile(ELECT "cp.async.bulk.prefetch.L2.global [%0], %1;\n}\n" ::"l"(p), "r"(bytes) : "memory");
}
__device__ __forceinline__ void e_store3d(const CUtensorMap* m, uint32_t src, int c1, int c2) {
  asm volatile(ELECT "cp.async.bulk.tensor.3d.global.shared::cta.bulk_group [%0, {%4,%2,%3}], [%1];\n"
               "@p cp.async.bulk.commit_group;\n@p cp.async.bulk.wait_group.read 0;\n}\n"
               ::"l"(m), "r"(src), "r"(c1), "r"(c2), "r"(0) : "memory");
}
__host__ __device__ constexpr uint64_t mkdesc(uint32_t addr, uint32_t lbo, uint32_t sbo, int swz) {
  return (uint64_t)((addr & 0x3FFFF) >> 4) | ((uint64_t)(lbo >> 4) << 16) | ((uint64_t)(sbo >> 4) << 32) |
         ((uint64_t)swz << 62);
}
#define WG_FENCE() asm volatile("wgmma.fence.sync.aligned;" ::: "memory")
#define WG_COMMIT() asm volatile("wgmma.commit_group.sync.aligned;" ::: "memory")
#define WG_WAIT(n) asm volatile("wgmma.wait_group.sync.aligned " #n ";" ::: "memory")

__device__ __forceinline__ void mma(float& d0, float& d1, float& d2, float& d3, uint32_t a0, uint32_t a1, uint32_t a2,
                                    uint32_t a3, uint32_t b0, uint32_t b1) {
  asm volatile("mma.sync.aligned.m16n8k16.row.col.f32.bf16.bf16.f32 {%0,%1,%2,%3},{%4,%5,%6,%7},{%8,%9},{%0,%1,%2,%3};"
               : "+f"(d0), "+f"(d1), "+f"(d2), "+f"(d3)
               : "r"(a0), "r"(a1), "r"(a2), "r"(a3), "r"(b0), "r"(b1));
}
__device__ __forceinline__ void mmac(float (&d)[4], uint32_t a0, uint32_t a1, uint32_t a2, uint32_t a3, uint32_t b0,
                                     uint32_t b1, const float (&c)[4]) {
  asm volatile("mma.sync.aligned.m16n8k16.row.col.f32.bf16.bf16.f32 {%0,%1,%2,%3},{%4,%5,%6,%7},{%8,%9},{%10,%11,%12,%13};"
               : "=f"(d[0]), "=f"(d[1]), "=f"(d[2]), "=f"(d[3])
               : "r"(a0), "r"(a1), "r"(a2), "r"(a3), "r"(b0), "r"(b1), "f"(c[0]), "f"(c[1]), "f"(c[2]), "f"(c[3]));
}
__device__ __forceinline__ void mma_p(int p, float (&d)[4], uint32_t a0, uint32_t a1, uint32_t a2, uint32_t a3, uint32_t b0, uint32_t b1) {
  asm volatile("{\n.reg .pred q;\nsetp.ne.b32 q, %10, 0;\n"
               "@q mma.sync.aligned.m16n8k16.row.col.f32.bf16.bf16.f32 {%0,%1,%2,%3},{%4,%5,%6,%7},{%8,%9},{%0,%1,%2,%3};\n}\n"
               : "+f"(d[0]), "+f"(d[1]), "+f"(d[2]), "+f"(d[3])
               : "r"(a0), "r"(a1), "r"(a2), "r"(a3), "r"(b0), "r"(b1), "r"(p));
}
__device__ __forceinline__ void mmac_p(int p, float (&d)[4], uint32_t a0, uint32_t a1, uint32_t a2, uint32_t a3, uint32_t b0,
                                       uint32_t b1, const float (&c)[4]) {
  asm volatile("{\n.reg .pred q;\nsetp.ne.b32 q, %14, 0;\n"
               "@q mma.sync.aligned.m16n8k16.row.col.f32.bf16.bf16.f32 {%0,%1,%2,%3},{%4,%5,%6,%7},{%8,%9},{%10,%11,%12,%13};\n}\n"
               : "+f"(d[0]), "+f"(d[1]), "+f"(d[2]), "+f"(d[3])
               : "r"(a0), "r"(a1), "r"(a2), "r"(a3), "r"(b0), "r"(b1), "f"(c[0]), "f"(c[1]), "f"(c[2]), "f"(c[3]), "r"(p));
}
__device__ __forceinline__ void mma_h(float (&d)[4], const uint32_t (&a)[4], uint32_t b0, uint32_t b1) {
  asm volatile("mma.sync.aligned.m16n8k16.row.col.f32.f16.f16.f32 {%0,%1,%2,%3},{%4,%5,%6,%7},{%8,%9},{%0,%1,%2,%3};"
               : "+f"(d[0]), "+f"(d[1]), "+f"(d[2]), "+f"(d[3]) : "r"(a[0]), "r"(a[1]), "r"(a[2]), "r"(a[3]), "r"(b0), "r"(b1));
}
__device__ __forceinline__ void mma_k8(float (&d)[4], uint32_t a0, uint32_t a1, uint32_t b0) {
  asm volatile("mma.sync.aligned.m16n8k8.row.col.f32.bf16.bf16.f32 {%0,%1,%2,%3},{%4,%5},{%6},{%0,%1,%2,%3};"
               : "+f"(d[0]), "+f"(d[1]), "+f"(d[2]), "+f"(d[3]) : "r"(a0), "r"(a1), "r"(b0));
}
__device__ __forceinline__ void mma0(float& d0, float& d1, float& d2, float& d3, uint32_t a0, uint32_t a1, uint32_t a2,
                                     uint32_t a3, uint32_t b0, uint32_t b1) {
  asm volatile("mma.sync.aligned.m16n8k16.row.col.f32.bf16.bf16.f32 {%0,%1,%2,%3},{%4,%5,%6,%7},{%8,%9},{%10,%10,%10,%10};"
               : "=f"(d0), "=f"(d1), "=f"(d2), "=f"(d3)
               : "r"(a0), "r"(a1), "r"(a2), "r"(a3), "r"(b0), "r"(b1), "f"(0.f));
}
__device__ __forceinline__ uint32_t pack_bf(float lo, float hi) {
  uint32_t r;
  asm("cvt.rn.bf16x2.f32 %0, %1, %2;" : "=r"(r) : "f"(hi), "f"(lo));
  return r;
}
__device__ __forceinline__ float bf_lo(uint32_t w) { return __uint_as_float(w << 16); }
__device__ __forceinline__ float bf_hi(uint32_t w) { return __uint_as_float(w & 0xffff0000u); }
__device__ __forceinline__ float bf_round(float x) { return __bfloat162float(__float2bfloat16_rn(x)); }
__device__ __forceinline__ uint32_t bmax2(uint32_t a, uint32_t b) {
  uint32_t r; asm("max.bf16x2 %0, %1, %2;" : "=r"(r) : "r"(a), "r"(b)); return r;
}
__device__ __forceinline__ uint32_t bmin2(uint32_t a, uint32_t b) {
  uint32_t r; asm("min.bf16x2 %0, %1, %2;" : "=r"(r) : "r"(a), "r"(b)); return r;
}
__device__ __forceinline__ float ex2(float x) { float r; asm("ex2.approx.ftz.f32 %0, %1;" : "=f"(r) : "f"(x)); return r; }
__device__ __forceinline__ float rcp(float x) { float r; asm("rcp.approx.ftz.f32 %0, %1;" : "=f"(r) : "f"(x)); return r; }
__device__ __forceinline__ void ldsm4(uint32_t (&r)[4], uint32_t a) {
  asm volatile("ldmatrix.sync.aligned.m8n8.x4.shared.b16 {%0,%1,%2,%3}, [%4];"
               : "=r"(r[0]), "=r"(r[1]), "=r"(r[2]), "=r"(r[3]) : "r"(a) : "memory");
}
__device__ __forceinline__ void ldsm4t(uint32_t (&r)[4], uint32_t a) {
  asm volatile("ldmatrix.sync.aligned.m8n8.x4.trans.shared.b16 {%0,%1,%2,%3}, [%4];"
               : "=r"(r[0]), "=r"(r[1]), "=r"(r[2]), "=r"(r[3]) : "r"(a) : "memory");
}
__device__ __forceinline__ void stsm4(uint32_t a, uint32_t r0, uint32_t r1, uint32_t r2, uint32_t r3) {
  asm volatile("stmatrix.sync.aligned.m8n8.x4.shared.b16 [%0], {%1,%2,%3,%4};"
               ::"r"(a), "r"(r0), "r"(r1), "r"(r2), "r"(r3) : "memory");
}
__device__ __forceinline__ uint32_t lds32(uint32_t a) {
  uint32_t r; asm volatile("ld.shared.u32 %0, [%1];" : "=r"(r) : "r"(a) : "memory"); return r;
}
__device__ __forceinline__ uint32_t lds16(uint32_t a) {
  uint32_t r; asm volatile("{\n.reg .u16 h;\nld.shared.u16 h, [%1];\ncvt.u32.u16 %0, h;\n}\n" : "=r"(r) : "r"(a) : "memory"); return r;
}
__device__ __forceinline__ uint2 lds64(uint32_t a) {
  uint2 r; asm volatile("ld.shared.v2.u32 {%0,%1}, [%2];" : "=r"(r.x), "=r"(r.y) : "r"(a) : "memory"); return r;
}
__device__ __forceinline__ uint4 lds128(uint32_t a) {
  uint4 r;
  asm volatile("ld.shared.v4.u32 {%0,%1,%2,%3}, [%4];" : "=r"(r.x), "=r"(r.y), "=r"(r.z), "=r"(r.w) : "r"(a) : "memory");
  return r;
}
__device__ __forceinline__ void sts32(uint32_t a, uint32_t v) { asm volatile("st.shared.u32 [%0], %1;" ::"r"(a), "r"(v) : "memory"); }
__device__ __forceinline__ void sts16(uint32_t a, uint32_t v) {
  asm volatile("{\n.reg .u16 h;\ncvt.u16.u32 h, %1;\nst.shared.u16 [%0], h;\n}\n" ::"r"(a), "r"(v) : "memory");
}
__device__ __forceinline__ void sts64(uint32_t a, uint32_t x, uint32_t y) {
  asm volatile("st.shared.v2.u32 [%0], {%1,%2};" ::"r"(a), "r"(x), "r"(y) : "memory");
}
__device__ __forceinline__ void sts128(uint32_t a, uint32_t x, uint32_t y, uint32_t z, uint32_t w) {
  asm volatile("st.shared.v4.u32 [%0], {%1,%2,%3,%4};" ::"r"(a), "r"(x), "r"(y), "r"(z), "r"(w) : "memory");
}
__device__ __forceinline__ uint4 ld_x(const uint4* p) {
  uint4 r;
  asm volatile("{\n.reg .b128 t;\nld.relaxed.gpu.global.b128 t, [%4];\nmov.b128 {%0,%1,%2,%3}, t;\n}\n"
               : "=r"(r.x), "=r"(r.y), "=r"(r.z), "=r"(r.w) : "l"(p) : "memory");
  return r;
}
__device__ __forceinline__ uint32_t ld_x32(const uint32_t* p) {
  uint32_t r; asm volatile("ld.relaxed.gpu.global.u32 %0, [%1];" : "=r"(r) : "l"(p) : "memory"); return r;
}
__device__ __forceinline__ void st_x(uint4* p, uint32_t x, uint32_t y, uint32_t z, uint32_t w) {
  asm volatile("{\n.reg .b128 t;\nmov.b128 t, {%1,%2,%3,%4};\nst.relaxed.gpu.global.b128 [%0], t;\n}\n"
               ::"l"(p), "r"(x), "r"(y), "r"(z), "r"(w) : "memory");
}
__device__ __forceinline__ void st_x_p(int p, uint4* a, uint32_t x, uint32_t y, uint32_t z, uint32_t w) {
  asm volatile("{\n.reg .b128 t;\n.reg .pred q;\nsetp.ne.b32 q, %5, 0;\nmov.b128 t, {%1,%2,%3,%4};\n@q st.relaxed.gpu.global.b128 [%0], t;\n}\n"
               ::"l"(a), "r"(x), "r"(y), "r"(z), "r"(w), "r"(p) : "memory");
}
__device__ __forceinline__ void sts64_p(int p, uint32_t a, uint32_t x, uint32_t y) {
  asm volatile("{\n.reg .pred q;\nsetp.ne.b32 q, %3, 0;\n@q st.shared.v2.u32 [%0], {%1,%2};\n}\n" ::"r"(a), "r"(x), "r"(y), "r"(p) : "memory");
}
__device__ __forceinline__ void st_x32(uint32_t* p, uint32_t x) {
  asm volatile("st.relaxed.gpu.global.u32 [%0], %1;" ::"l"(p), "r"(x) : "memory");
}
__device__ __forceinline__ uint32_t nz(uint32_t w) { return max(w, 1u); }
__device__ __forceinline__ uint32_t fu(float x) { return __float_as_uint(x); }
__device__ __forceinline__ float uf(uint32_t x) { return __uint_as_float(x); }

__device__ __forceinline__ void wgmma_ss_n96(float (&d)[48], uint64_t da, uint64_t db, int sc) {
  asm volatile("{\n.reg .pred p;\nsetp.ne.b32 p, %50, 0;\n"
      "wgmma.mma_async.sync.aligned.m64n96k16.f32.bf16.bf16 "
      "{%0,%1,%2,%3,%4,%5,%6,%7,%8,%9,%10,%11,%12,%13,%14,%15,%16,%17,%18,%19,%20,%21,%22,%23,%24,%25,%26,%27,%28,%29,%30,%31,%32,%33,%34,%35,%36,%37,%38,%39,%40,%41,%42,%43,%44,%45,%46,%47}, "
      "%48, %49, p, 1, 1, 0, 1;\n}\n"
      : "+f"(d[0]), "+f"(d[1]), "+f"(d[2]), "+f"(d[3]), "+f"(d[4]), "+f"(d[5]), "+f"(d[6]), "+f"(d[7]),
        "+f"(d[8]), "+f"(d[9]), "+f"(d[10]), "+f"(d[11]), "+f"(d[12]), "+f"(d[13]), "+f"(d[14]), "+f"(d[15]),
        "+f"(d[16]), "+f"(d[17]), "+f"(d[18]), "+f"(d[19]), "+f"(d[20]), "+f"(d[21]), "+f"(d[22]), "+f"(d[23]),
        "+f"(d[24]), "+f"(d[25]), "+f"(d[26]), "+f"(d[27]), "+f"(d[28]), "+f"(d[29]), "+f"(d[30]), "+f"(d[31]),
        "+f"(d[32]), "+f"(d[33]), "+f"(d[34]), "+f"(d[35]), "+f"(d[36]), "+f"(d[37]), "+f"(d[38]), "+f"(d[39]),
        "+f"(d[40]), "+f"(d[41]), "+f"(d[42]), "+f"(d[43]), "+f"(d[44]), "+f"(d[45]), "+f"(d[46]), "+f"(d[47])
      : "l"(da), "l"(db), "r"(sc));
}

__device__ __forceinline__ void wgmma_ss_n128(float (&d)[64], uint64_t da, uint64_t db, int sc) {
  asm volatile("{\n.reg .pred p;\nsetp.ne.b32 p, %66, 0;\n"
      "wgmma.mma_async.sync.aligned.m64n128k16.f32.bf16.bf16 "
      "{%0,%1,%2,%3,%4,%5,%6,%7,%8,%9,%10,%11,%12,%13,%14,%15,%16,%17,%18,%19,%20,%21,%22,%23,%24,%25,%26,%27,%28,%29,%30,%31,%32,%33,%34,%35,%36,%37,%38,%39,%40,%41,%42,%43,%44,%45,%46,%47,%48,%49,%50,%51,%52,%53,%54,%55,%56,%57,%58,%59,%60,%61,%62,%63}, "
      "%64, %65, p, 1, 1, 0, 1;\n}\n"
      : "+f"(d[0]), "+f"(d[1]), "+f"(d[2]), "+f"(d[3]), "+f"(d[4]), "+f"(d[5]), "+f"(d[6]), "+f"(d[7]),
        "+f"(d[8]), "+f"(d[9]), "+f"(d[10]), "+f"(d[11]), "+f"(d[12]), "+f"(d[13]), "+f"(d[14]), "+f"(d[15]),
        "+f"(d[16]), "+f"(d[17]), "+f"(d[18]), "+f"(d[19]), "+f"(d[20]), "+f"(d[21]), "+f"(d[22]), "+f"(d[23]),
        "+f"(d[24]), "+f"(d[25]), "+f"(d[26]), "+f"(d[27]), "+f"(d[28]), "+f"(d[29]), "+f"(d[30]), "+f"(d[31]),
        "+f"(d[32]), "+f"(d[33]), "+f"(d[34]), "+f"(d[35]), "+f"(d[36]), "+f"(d[37]), "+f"(d[38]), "+f"(d[39]),
        "+f"(d[40]), "+f"(d[41]), "+f"(d[42]), "+f"(d[43]), "+f"(d[44]), "+f"(d[45]), "+f"(d[46]), "+f"(d[47]),
        "+f"(d[48]), "+f"(d[49]), "+f"(d[50]), "+f"(d[51]), "+f"(d[52]), "+f"(d[53]), "+f"(d[54]), "+f"(d[55]),
        "+f"(d[56]), "+f"(d[57]), "+f"(d[58]), "+f"(d[59]), "+f"(d[60]), "+f"(d[61]), "+f"(d[62]), "+f"(d[63])
      : "l"(da), "l"(db), "r"(sc));
}

__device__ __forceinline__ void wgmma_rs_n16(float (&d)[8], const uint4& a, uint64_t db, int sc) {
  asm volatile("{\n.reg .pred p;\nsetp.ne.b32 p, %13, 0;\n"
      "wgmma.mma_async.sync.aligned.m64n16k16.f32.bf16.bf16 "
      "{%0,%1,%2,%3,%4,%5,%6,%7}, "
      "{%8,%9,%10,%11}, %12, p, 1, 1, 1;\n}\n"
      : "+f"(d[0]), "+f"(d[1]), "+f"(d[2]), "+f"(d[3]), "+f"(d[4]), "+f"(d[5]), "+f"(d[6]), "+f"(d[7])
      : "r"(a.x), "r"(a.y), "r"(a.z), "r"(a.w), "l"(db), "r"(sc));
}

struct Params {
  const __nv_bfloat16 *logA, *Aim, *Cre, *Cim, *logdt, *Dskip, *x, *wphi, *wo;
  __nv_bfloat16* out;
  uint4* xs;
  long long* ts;
};

__device__ __forceinline__ uint4 tr_row(const uint4 (&v)[8], int i) {
  uint32_t o[4];
#pragma unroll
  for (int m = 0; m < 4; m++) {
    const uint4 &ra = v[2 * m], &rb = v[2 * m + 1];
    const int k = i >> 1;
    const uint32_t xa = k == 0 ? ra.x : k == 1 ? ra.y : k == 2 ? ra.z : ra.w;
    const uint32_t xb = k == 0 ? rb.x : k == 1 ? rb.y : k == 2 ? rb.z : rb.w;
    o[m] = __byte_perm(xa, xb, (i & 1) ? 0x7632 : 0x5410);
  }
  return make_uint4(o[0], o[1], o[2], o[3]);
}

struct cpx { float r, i; };
__device__ __forceinline__ cpx csq(cpx a) { return {a.r * a.r - a.i * a.i, 2.f * (a.r * a.i)}; }
__device__ __forceinline__ cpx polar(float e, float t) {
  const float m = ex2(e);
  return {m * __cosf(t), m * __sinf(t)};
}

struct KgenRaw { unsigned short la, ai, cr, ci, ldt; };
__device__ __forceinline__ KgenRaw kgen_load(const Params& P, int d, int unit, int lane) {
  const int o = d * 128 + unit * 32 + lane;
  return {__ldg((const unsigned short*)P.logA + o), __ldg((const unsigned short*)P.Aim + o), __ldg((const unsigned short*)P.Cre + o),
          __ldg((const unsigned short*)P.Cim + o), __ldg((const unsigned short*)P.logdt + d)};
}
struct hmul { __half2 a, b; };
__device__ __forceinline__ hmul mk_mul(cpx w) { return {__floats2half2_rn(w.r, w.i), __floats2half2_rn(-w.i, w.r)}; }
__device__ __forceinline__ __half2 hcm(__half2 z, const hmul& w) { return __hfma2(__high2half2(z), w.b, __hmul2(__low2half2(z), w.a)); }
__device__ __forceinline__ uint32_t hu(__half2 v) { return *(const uint32_t*)&v; }

__device__ __forceinline__ void kgen_unit(const KgenRaw& r, int lane, uint32_t buf, uint32_t zero, float (&k)[5][4], float& k2048) {
  const float dt = bf_round(expf(bf_lo(r.ldt)));
  const float a2 = -(bf_round(expf(bf_lo(r.la))) * dt) * 1.4426950408889634f;
  const float f = bf_lo(r.ai) * dt;
  const float r128 = f * 20.371832715762604f;
  const uint32_t ex = min(max(__reduce_max_sync(0xffffffffu, max(r.cr & 0x7fffu, r.ci & 0x7fffu)) >> 7, 1u), 253u);
  const float cs = uf((254u - ex) << 23), sc = 2.f * dt * uf(ex << 23);
  const cpx C = {bf_lo(r.cr) * cs, -bf_lo(r.ci) * cs};
  const uint32_t sa = buf + (lane & 7) * 128 + ((((lane >> 3) ^ lane) & 7) << 4);
  const uint32_t lb = buf + (lane >> 3) * 128 + (((lane ^ (lane >> 3)) & 7) << 4);
  const uint32_t la = buf + ((lane >> 3) & 1) * 1024 + (lane >> 4) * 128 + (((lane ^ (lane >> 4)) & 7) << 4);
  auto put = [&](const __half2 (&v)[8], uint32_t off) {
    stsm4(sa + off, hu(v[0]), hu(v[1]), hu(v[2]), hu(v[3]));
    stsm4((sa ^ 64) + off, hu(v[4]), hu(v[5]), hu(v[6]), hu(v[7]));
  };
  uint32_t A[4][4], B[5][2][4];
  auto get = [&](int j, uint32_t off) {
    __syncwarp();
    ldsm4(B[j][0], lb + off);
    ldsm4(B[j][1], (lb ^ 64) + 512 + off);
  };
  auto tile = [&](int j) {
    k[j][0] = k[j][1] = k[j][2] = k[j][3] = 0.f;
#pragma unroll
    for (int s = 0; s < 4; s++) mma_h(k[j], A[s], B[j][s >> 1][2 * (s & 1)], B[j][s >> 1][2 * (s & 1) + 1]);
  };
  auto after = [&](cpx v, uint32_t dep) { return cpx{uf(fu(v.r) ^ (dep & zero)), v.i}; };
  const cpx w1 = polar(a2, f), w128 = polar(a2 * 128.f, (r128 - rintf(r128)) * 6.283185307179586f);
  const cpx w2 = csq(w1), w4 = csq(w2);
  __half2 t0[8], t1[8], t2[8], t3[8], t4[8];
  const hmul m2 = mk_mul(w2), m4 = mk_mul(w4), m128 = mk_mul(w128);
  t0[0] = __floats2half2_rn(1.f, 0.f); t0[1] = __floats2half2_rn(w1.r, w1.i); t0[2] = m2.a; t0[4] = m4.a;
  t0[3] = hcm(t0[1], m2); t0[5] = hcm(t0[1], m4); t0[6] = hcm(t0[2], m4); t0[7] = hcm(t0[3], m4);
  put(t0, 0); get(0, 0);
  t1[0] = m128.a;
#pragma unroll
  for (int i = 1; i < 8; i++) t1[i] = hcm(t0[i], m128);
  put(t1, 1024); get(1, 1024);
  {
    cpx w8 = csq(after(w4, B[0][0][0]));
    w8.i = -w8.i;
    const cpx w16 = csq(w8), w32 = csq(w16), w64 = csq(w32);
    const hmul m8 = mk_mul(w8), m16 = mk_mul(w16), m32 = mk_mul(w32), m64 = mk_mul(w64);
    __half2 a[8];
    a[0] = __floats2half2_rn(C.r, C.i); a[1] = hcm(a[0], m8);
    a[2] = hcm(a[0], m16); a[3] = hcm(a[1], m16);
#pragma unroll
    for (int i = 0; i < 4; i++) a[4 + i] = hcm(a[i], m32);
    put(a, 0);
#pragma unroll
    for (int i = 0; i < 8; i++) a[i] = hcm(a[i], m64);
    put(a, 1024);
    __syncwarp();
#pragma unroll
    for (int s = 0; s < 4; s++) ldsm4(A[s], (la ^ (s << 5)) + s * 256);
  }
  const cpx w256 = csq(after(w128, B[1][0][0]));
  const hmul m256 = mk_mul(w256);
  t2[0] = m256.a;
#pragma unroll
  for (int i = 1; i < 8; i++) t2[i] = hcm((i & 1) ? t1[i & 6] : t0[i & 6], m256);
  put(t2, 0); get(2, 0);
  tile(0); tile(1);
  const cpx w512 = csq(after(w256, A[0][0]));
  const hmul m512 = mk_mul(w512);
  t3[0] = m512.a;
#pragma unroll
  for (int i = 1; i < 8; i++) t3[i] = hcm((i & 2) ? t2[i & 5] : ((i & 1) ? t1[i & 4] : t0[i & 4]), m512);
  put(t3, 1024); get(3, 1024);
  tile(2);
  const cpx w1024 = csq(after(w512, B[2][0][0])), we = csq(w1024);
  const hmul m1024 = mk_mul(w1024);
  t4[0] = m1024.a;
#pragma unroll
  for (int i = 1; i < 8; i++) t4[i] = hcm((i & 4) ? t3[i & 3] : ((i & 2) ? t2[i & 1] : t1[0]), m1024);
  put(t4, 0); get(4, 0);
  tile(3); tile(4);
  k2048 = (C.r * we.r + C.i * we.i) * sc;
#pragma unroll
  for (int j = 0; j < 5; j++) { k[j][0] *= sc; k[j][1] *= sc; k[j][2] *= sc; k[j][3] *= sc; }
}

__device__ __forceinline__ void build_tables(uint32_t tb, int lane, float (&k)[5][4], float k2048) {
  const int g = lane >> 2, c = lane & 3;
  const uint32_t kc = tb + T_KC + 16;
  {
    const uint32_t a0 = kc + 16 * g + 4 * c, a2 = kc + 2 * (256 + 4 * g + c);
    const uint32_t a3 = kc + 2 * (384 + 2 * g + 64 * (c & 1) + (c >> 1)), a4 = kc + 2 * (512 + g + 32 * c);
#pragma unroll
    for (int r = 0; r < 2; r++) {
      sts32(a0 + 128 * r, pack_bf(k[0][2 * r], k[0][2 * r + 1]));
      sts32(a0 + 128 * r + 256, pack_bf(k[1][2 * r], k[1][2 * r + 1]));
      const uint32_t w2 = pack_bf(k[2][2 * r], k[2][2 * r + 1]);
      const uint32_t w3 = pack_bf(k[3][2 * r], k[3][2 * r + 1]);
      const uint32_t w4 = pack_bf(k[4][2 * r], k[4][2 * r + 1]);
      sts16(a2 + 64 * r, w2); sts16(a2 + 64 * r + 128, w2 >> 16);
      sts16(a3 + 32 * r, w3); sts16(a3 + 32 * r + 64, w3 >> 16);
      sts16(a4 + 16 * r, w4); sts16(a4 + 16 * r + 32, w4 >> 16);
    }
  }
  if (lane == 0) { sts16(kc + 2 * 640, pack_bf(k2048, 0.f)); sts16(kc - 2, 0); }
  __syncwarp();
  const uint32_t td = tb + T_D + 32;
  {
    const uint4 v = lds128(kc + 16 * lane);
    const uint32_t pv = lds16(kc + 16 * lane - 2);
    sts128(td + 32 * lane, __byte_perm(v.x, pv, 0x5410), __byte_perm(v.x, v.x, 0x1032), __byte_perm(v.y, v.x, 0x7610),
           __byte_perm(v.y, v.y, 0x1032));
    sts128(td + 32 * lane + 16, __byte_perm(v.z, v.y, 0x7610), __byte_perm(v.z, v.z, 0x1032),
           __byte_perm(v.w, v.z, 0x7610), __byte_perm(v.w, v.w, 0x1032));
  }
  {
    const uint2 v = lds64(kc + 512 + 8 * lane);
    const uint32_t k4 = lds16(kc + 512 + 8 * lane + 8);
    const uint32_t pv = lds16(kc + (lane == 0 ? 510 : 512 + 8 * lane));
    const uint32_t k22 = __byte_perm(v.y, v.y, 0x1010);
    sts128(td + 1024 + 32 * lane, __byte_perm(v.x, pv, 0x5410), __byte_perm(v.x, v.x, 0x1010),
           __byte_perm(v.x, v.x, 0x1032), __byte_perm(v.y, v.x, 0x7610));
    sts128(td + 1024 + 32 * lane + 16, k22, k22, __byte_perm(v.y, v.y, 0x1032), __byte_perm(k4, v.y, 0x7610));
  }
  {
    const uint32_t kk = lds16(kc + 2 * 384);
    const uint32_t w = lane < 3 ? (kk | (kk << 16)) : (lane == 3 ? (kk << 16) : 0u);
    if (lane < 24) sts32(td + 4 * (lane < 16 ? 512 + lane : lane - 24), w);
    const uint32_t lo_ = lds16(kc + 2 * 511), le_ = lds16(kc + 2 * 512);
    const uint32_t ja = tb + T_5 + (lane < 16 ? 4 * lane : 256 + 4 * lane);
    sts32(ja, lane == 16 ? (le_ << 16) : 0u);
    sts32(ja + 384, lane == 16 ? (lo_ << 16) : 0u);
    sts32(tb + (lane < 16 ? T_7 : T_9 - 64) + 4 * lane, 0u);
  }
#pragma unroll
  for (int s = 0; s < 2; s++) {
    const uint32_t b = kc + 2 * (s ? 512 : 384) + 8 * lane;
    const uint2 v = lds64(b);
    uint32_t em = lds16(b - 2), e0 = v.x;
    const uint32_t e4 = lds16(b + 8);
    if (lane == 0) { em = 0; e0 = 0; }
    sts64(tb + (s ? T_7 : T_3) + 64 + 8 * lane, __byte_perm(v.x, em, 0x5432), __byte_perm(v.y, v.x, 0x7632));
    sts64(tb + (s ? T_9 : T_5) + 64 + 8 * lane, __byte_perm(v.y, e0, 0x5410), __byte_perm(e4, v.y, 0x5410));
  }
  __syncwarp();
}

__device__ __forceinline__ uint32_t box2w(int lo, int n, int o) {
  return ((unsigned)(o - lo) < (unsigned)n ? 0x3F80u : 0u) | ((unsigned)(o + 1 - lo) < (unsigned)n ? 0x3F800000u : 0u);
}

__device__ __forceinline__ void conv_channel(uint32_t ub, uint32_t tb, int lane, uint4* ydst) {
  const int g = lane >> 2, c = lane & 3, x = g - 2 * c;
  const uint32_t st = tb + T_ST + lane * 8;
  const int mi = lane >> 3;
  const uint32_t qa = ub + U_PAD + 16 * (lane & 7) + ((mi == 0 || mi == 3) ? U_ODD : 0) - (mi == 0 ? 16 : 0);
  const uint32_t kv = lds16(tb + T_KC + 16 + 2 * 512);
  {
    const uint32_t hb = ub + U_PAD + (mi & 1) * U_ODD + 16 * ((lane >> 4) + (lane & 7)) - 16;
    const int oh = c < 2 ? 8 + 2 * c : 2 * c - 8;
    const uint32_t bx0 = box2w(g - 4, 9, 2 * c), bx1 = box2w(g - 3, 7, 2 * c), bx2 = box2w(g - 4, 9, oh), bx3 = box2w(g - 3, 7, oh);
    uint32_t f7[9], f9a[9], f9b[9];
    const uint32_t fa = tb + T_7 + 4 * (8 + x);
#pragma unroll
    for (int m = 0; m < 9; m++) {
      f7[m] = lds32(fa + 32 * m);
      f9b[m] = lds32(fa + 320 + 32 * m);
      f9a[m] = lds32(fa + 316 + 32 * m);
    }
    mbar_wait(BAR(MB_EMPTY + 15));
    TS(36);
    uint32_t z09[8], z07[8], zm9[8], zm7[8];
#pragma unroll
    for (int i = 0; i < 8; i++) {
      uint32_t h[4];
      ldsm4(h, hb + 128 * i);
      float y0, y1, y2, y3, w0, w1, w2, w3;
      mma0(y0, y1, y2, y3, bx0, bx1, bx2, bx3, h[2], c < 2 ? h[3] : h[1]);
      mma0(w0, w1, w2, w3, bx0, bx1, bx2, bx3, h[1], c < 2 ? h[2] : h[0]);
      z09[i] = pack_bf(y0, y1); z07[i] = pack_bf(y2, y3);
      zm9[i] = pack_bf(w0, w1); zm7[i] = pack_bf(w2, w3);
    }
    float a[4][2][4];
#pragma unroll
    for (int kap = 0; kap < 4; kap++)
#pragma unroll
      for (int sg = 0; sg < 2; sg++)
#pragma unroll
        for (int bk = 3; bk >= kap; bk--) {
          const int m = 2 * (bk - kap) + 1;
          float(&a0)[4] = a[bk][0];
          float(&a1)[4] = a[bk][1];
          if (sg == 0 && kap == 0) {
            mma0(a0[0], a0[1], a0[2], a0[3], f9a[m], f9a[m + 1], f9a[m - 1], f9a[m], z09[0], z09[1]);
            mma0(a1[0], a1[1], a1[2], a1[3], f9b[m], f9b[m + 1], f9b[m - 1], f9b[m], zm9[0], zm9[1]);
          } else if (sg == 0) {
            mma(a0[0], a0[1], a0[2], a0[3], f9a[m], f9a[m + 1], f9a[m - 1], f9a[m], z09[2 * kap], z09[2 * kap + 1]);
            mma(a1[0], a1[1], a1[2], a1[3], f9b[m], f9b[m + 1], f9b[m - 1], f9b[m], zm9[2 * kap], zm9[2 * kap + 1]);
          } else {
            mma(a0[0], a0[1], a0[2], a0[3], f7[m], f7[m + 1], f7[m - 1], f7[m], zm7[2 * kap], zm7[2 * kap + 1]);
            mma(a1[0], a1[1], a1[2], a1[3], f7[m], f7[m + 1], f7[m - 1], f7[m], z07[2 * kap], z07[2 * kap + 1]);
          }
        }
#pragma unroll
    for (int bk = 0; bk < 4; bk++) {
      sts64(st + 256 * (8 + 2 * bk), pack_bf(a[bk][0][0], a[bk][0][1]), pack_bf(a[bk][1][0], a[bk][1][1]));
      sts64(st + 256 * (9 + 2 * bk), pack_bf(a[bk][0][2], a[bk][0][3]), pack_bf(a[bk][1][2], a[bk][1][3]));
    }
  }
  TS(44);
  {
    const int oh = c < 3 ? 2 * c : -10;
    const uint32_t bx0 = box2w(g - 10, 5, 2 * c - 8), bx1 = box2w(g - 5, 3, 2 * c - 8), bx2 = box2w(g - 10, 5, oh), bx3 = box2w(g - 5, 3, oh);
    const uint32_t lb0 = ((unsigned)(x + 5) < 2u ? kv : 0u) | ((unsigned)(x + 4) < 2u ? kv << 16 : 0u);
    const uint32_t lb1 = ((unsigned)(x - 3) < 2u ? kv : 0u) | ((unsigned)(x - 4) < 2u ? kv << 16 : 0u);
    const int q0 = g - 1, q1 = c < 3 ? g : g - 2;
    uint32_t y0a = ub + U_PAD + (q0 & 1) * U_ODD + 16 * (q0 >> 1) + 4 * c;
    uint32_t y1a = ub + U_PAD + (q1 & 1) * U_ODD + 16 * (q1 >> 1) + 4 * c;
    uint2 a5[10], a3[10];
    const uint32_t aa = tb + T_5 + 4 * (8 + 2 * g - 2 * c);
#pragma unroll
    for (int m = 0; m < 10; m++) { a5[m] = lds64(aa + 32 * m); a3[m] = lds64(aa + 384 + 32 * m); }
    float T[6][4];
#pragma unroll
    for (int i = 0; i < 6; i++) T[i][0] = T[i][1] = T[i][2] = T[i][3] = 0.f;
    uint32_t x5[2] = {0, 0}, x3[2] = {0, 0}, yb[4], lq[4];
    uint32_t lqa = qa, sta = st + 256 * 8;
    uint2 sv;
    auto fetch = [&]() {
      yb[0] = lds32(y0a); yb[1] = lds32(y1a); yb[2] = lds32(y0a + 64); yb[3] = lds32(y1a + 64);
      ldsm4(lq, lqa);
      sv = lds64(min(sta, st + 256 * 15));
      y0a += 128; y1a += 128; lqa += 128; sta += 256;
    };
    fetch();
#pragma unroll 2
    for (int kap = -1; kap < 13; kap++) {
      float yn[2][4];
      mma0(yn[0][0], yn[0][1], yn[0][2], yn[0][3], bx0, bx1, bx2, bx3, yb[0], yb[1]);
      mma0(yn[1][0], yn[1][1], yn[1][2], yn[1][3], bx0, bx1, bx2, bx3, yb[2], yb[3]);
      sts64_p(kap > 0, sta - 256 * 7, pack_bf(T[0][0], T[0][1]), pack_bf(T[0][2], T[0][3]));
#pragma unroll
      for (int i = 0; i < 5; i++)
        mmac_p((unsigned)kap < 12u - i, T[i], a5[2 * i + 1].x, a5[2 * i + 1].y, a5[2 * i].x, a5[2 * i].y, x5[0], x5[1], T[i + 1]);
      const float ci[4] = {bf_lo(sv.x), bf_hi(sv.x), bf_lo(sv.y), bf_hi(sv.y)};
      mmac_p(kap < 7, T[5], lq[0], lq[1], lq[2], lq[3], lb0, lb1, ci);
      fetch();
#pragma unroll
      for (int i = 0; i < 5; i++)
        mma_p((unsigned)kap < 12u - i, T[i], a3[2 * i + 1].x, a3[2 * i + 1].y, a3[2 * i].x, a3[2 * i].y, x3[0], x3[1]);
#pragma unroll
      for (int hh = 0; hh < 2; hh++) { x5[hh] = pack_bf(yn[hh][0], yn[hh][1]); x3[hh] = pack_bf(yn[hh][2], yn[hh][3]); }
    }
  }
  TS(45);
  {
    uint32_t F[66];
    const uint32_t fa = tb + T_D + 32 + 4 * x;
#pragma unroll
    for (int m = 0; m < 66; m++) F[m] = lds32(fa + 32 * m);
    float T[5][4];
#pragma unroll
    for (int i = 0; i < 5; i++) T[i][0] = T[i][1] = T[i][2] = T[i][3] = 0.f;
    uint32_t qd[8][4], held[2] = {0, 0};
    uint32_t qp = qa + 128 * 15, sta = st + 256 * 14;
    uint4* yd = ydst + 19 * 16;
#pragma unroll
    for (int i = 0; i < 6; i++) ldsm4(qd[i], qp - 16 * i);
    uint2 sv = lds64(sta + 256);
    float ci[4] = {bf_lo(sv.x), bf_hi(sv.x), bf_lo(sv.y), bf_hi(sv.y)};
    TS(46);
#pragma unroll 2
    for (int be = 15; be >= 0; be--) {
#pragma unroll
      for (int k = 4; k >= 1; k--)
        mmac_p(be <= 15 - k, T[k], qd[0][0], qd[0][1], qd[0][2], qd[0][3], F[16 * k + 1], F[16 * k], T[k - 1]);
      mmac(T[0], qd[0][0], qd[0][1], qd[0][2], qd[0][3], F[1], F[0], ci);
      ldsm4(qd[6], qp - 16 * 6);
      ldsm4(qd[7], qp - 16 * 7);
      sv = lds64(sta);
#pragma unroll
      for (int i = 1; i < 8; i++) {
#pragma unroll
        for (int k = 3; k >= 0; k--)
          mma_p(k == 0 || be <= 15 - k, T[k], qd[i][0], qd[i][1], qd[i][2], qd[i][3], F[16 * k + 2 * i + 1], F[16 * k + 2 * i]);
        if (i < 7) ldsm4(qd[i - 1], qp - 128 - 16 * (i - 1));
        if (i == 2) {
          const uint32_t w0 = pack_bf(T[4][0], T[4][1]), w1 = pack_bf(T[4][2], T[4][3]);
          st_x_p(be <= 10 && !(be & 1), yd, nz(w0), w1, held[0], held[1]);
          held[0] = w0; held[1] = w1;
        }
        if (i == 4) {
          if (be <= 4) sv = make_uint2(0, 0);
          ci[0] = bf_lo(sv.x); ci[1] = bf_hi(sv.x); ci[2] = bf_lo(sv.y); ci[3] = bf_hi(sv.y);
        }
      }
      qp -= 128; sta -= 256; yd -= 16;
    }
#pragma unroll
    for (int B = 1; B >= 0; B--)
      st_x(ydst + B * 32, nz(pack_bf(T[2 * B][0], T[2 * B][1])), pack_bf(T[2 * B][2], T[2 * B][3]),
           pack_bf(T[2 * B + 1][0], T[2 * B + 1][1]), pack_bf(T[2 * B + 1][2], T[2 * B + 1][3]));
  }
}

__device__ __forceinline__ void dual_exp(const uint32_t* w, uint32_t* e) {
  const float L = 1.44268798828125f;
  uint32_t mx = bmax2(bmax2(w[0], w[1]), bmax2(w[2], w[3]));
  uint32_t mn = bmin2(bmin2(w[0], w[1]), bmin2(w[2], w[3]));
  mx = bmax2(mx, __shfl_xor_sync(0xffffffffu, mx, 1));
  mn = bmin2(mn, __shfl_xor_sync(0xffffffffu, mn, 1));
  mx = bmax2(mx, __shfl_xor_sync(0xffffffffu, mx, 2));
  mn = bmin2(mn, __shfl_xor_sync(0xffffffffu, mn, 2));
  const float mx0 = bf_lo(mx) * -L, mx1 = bf_hi(mx) * -L, mn0 = bf_lo(mn) * L, mn1 = bf_hi(mn) * L;
#pragma unroll
  for (int i = 0; i < 2; i++) {
    const float a0 = bf_lo(w[2 * i]), a1 = bf_hi(w[2 * i]), b0 = bf_lo(w[2 * i + 1]), b1 = bf_hi(w[2 * i + 1]);
    e[2 * i] = pack_bf(ex2(fmaf(a0, L, mx0)), ex2(fmaf(b0, L, mx0)));
    e[2 * i + 1] = pack_bf(ex2(fmaf(a1, L, mx1)), ex2(fmaf(b1, L, mx1)));
    e[4 + 2 * i] = pack_bf(ex2(fmaf(a0, -L, mn0)), ex2(fmaf(b0, -L, mn0)));
    e[5 + 2 * i] = pack_bf(ex2(fmaf(a1, -L, mn1)), ex2(fmaf(b1, -L, mn1)));
  }
}
__device__ __forceinline__ void norm_store(const uint32_t* e, uint32_t dst) {
  float s[4];
  mma0(s[0], s[1], s[2], s[3], e[0], e[1], e[2], e[3], 0x3F803F80u, 0x3F803F80u);
  const uint32_t r = pack_bf(rcp(s[0]), rcp(s[2]));
  const __nv_bfloat162 rr = *(const __nv_bfloat162*)&r;
  uint32_t o[4];
#pragma unroll
  for (int i = 0; i < 4; i++) {
    const __nv_bfloat162 v = __hmul2(*(const __nv_bfloat162*)&e[i], (i & 1) ? __high2bfloat162(rr) : __low2bfloat162(rr));
    o[i] = *(const uint32_t*)&v;
  }
  stsm4(dst, o[0], o[1], o[2], o[3]);
}

__global__ void __launch_bounds__(NTHREADS, 1)
fused_kernel(const Params P, const __grid_constant__ CUtensorMap mx, const __grid_constant__ CUtensorMap mw,
             const __grid_constant__ CUtensorMap mo, const __grid_constant__ CUtensorMap mu,
             const __grid_constant__ CUtensorMap mout, const __grid_constant__ CUtensorMap mw4) {
  constexpr uint32_t sb = SB;
  const int tid = threadIdx.x, lane = tid & 31;
  const int warp = __shfl_sync(0xffffffffu, tid >> 5, 0);
  const int b = blockIdx.x, oct = b >> 3, i8 = b & 7;
  const int rt = oct < 8 ? oct : 15 - oct;
  const int hp = (oct >> 3) * 8 + i8;

  const int wg = warp >> 2, w = warp & 3;
  const int d = b * 4 + ((tid >> 5) & 3);
  if (tid < 384) {
    asm volatile("prefetch.tensormap [%0];" ::"l"(&mu) : "memory");
    asm volatile("prefetch.tensormap [%0];" ::"l"(&mw) : "memory");
    asm volatile("prefetch.tensormap [%0];" ::"l"(&mx) : "memory");
    asm volatile("prefetch.tensormap [%0];" ::"l"(&mw4) : "memory");
  }
  if (warp == 12) {
    if (lane == 0) {
#pragma unroll
      for (int i = 0; i < 9; i++) mbar_init(BAR(i), 1);
      asm volatile("fence.mbarrier_init.release.cluster;" ::: "memory");
    }
    __syncwarp();
    if (lane < 9) mbar_expect(BAR(0) + 8 * lane, lane == 5 ? 65536 : ((lane == 0 || lane > 5) ? 16384 : 28672));
    __syncwarp();
    e_tma3d(sb + OFF_W, &mw, BAR(MB_FULL), hp * 32, 0, 0);
    e_tma2d(sb + OFF_X + 3 * 16384, &mx, BAR(MB_FULL), 0, rt * 256);
  } else if (warp == 13) {
    if (lane == 0) {
#pragma unroll
      for (int i = 9; i < 39; i++) mbar_init(BAR(i), i < MB_EMPTY ? 1 : (i < MB_AUX ? 4 : 5));
      asm volatile("fence.mbarrier_init.release.cluster;" ::: "memory");
    }
    __syncwarp();
    if (lane < 9) mbar_expect(BAR(MB_FULL + 8) + 8 * lane, lane < 8 ? 16384 : 131072);
  }
  const KgenRaw raw = kgen_load(P, d, tid >> 7, lane);
  const unsigned short dsk = __ldg((const unsigned short*)P.Dskip + d);
  if (warp == 12) {
#pragma unroll 1
    for (int kb = 1; kb < 4; kb++) {
      e_tma3d(sb + OFF_W + kb * 12288, &mw, BAR(MB_FULL) + 8 * kb, hp * 32, kb * 64, 0);
      e_tma2d(sb + OFF_X + (kb < 2 ? kb + 3 : kb - 2) * 16384, &mx, BAR(MB_FULL) + 8 * kb, kb * 64, rt * 256);
    }
    e_tma5d(sb + OFF_STG0, &mu, BAR(MB_URAW), i8 * 64, oct * 4);
    e_prefetch(P.x + (size_t)(rt * 256 + hp * 16) * 512, 16384);
    e_tma4d(sb + OFF_W + 4 * 12288, &mw4, BAR(MB_FULL + 4), hp * 32, 4);
    if (smem_u32(smem_raw) != SB) __trap();
    if (lane == 0) TS1(54);
  }
  const uint32_t tb = sb + OFF_T + w * T_CH;
  float k[5][4], k2048;
  {
    const uint32_t kp = wg == 3 ? sb + OFF_X + 32768 + w * 4096 : tb + (wg & 1) * 2608;
    kgen_unit(raw, lane, wg == 2 ? sb + OFF_STG0 + 16384 + w * 2048 : (kp + 127) & ~127u, blockIdx.y, k, k2048);
    TS(40 + wg);
    k2048 += __shfl_xor_sync(0xffffffffu, k2048, 16);
    k2048 += __shfl_xor_sync(0xffffffffu, k2048, 8);
    if (wg != 2 || (fu(k[0][0]) & fu(k[1][0]) & fu(k[2][0]) & fu(k[3][0]) & fu(k[4][0])) == 0xffffffffu) {
#pragma unroll
      for (int j = 0; j < 5; j++) sts128(kp + j * 512 + lane * 16, fu(k[j][0]), fu(k[j][1]), fu(k[j][2]), fu(k[j][3]));
      if (lane < 8) sts32(kp + 2560 + lane * 4, fu(k2048));
    }
  }
  __syncthreads();
  if (warp >= 12) {
    asm volatile("setmaxnreg.dec.sync.aligned.u32 32;");
    if (warp == 12) {
      nb_sync(NB_KREAD, 160);
      asm volatile("fence.proxy.async.shared::cta;" ::: "memory");
      e_tma2d(sb + OFF_X + 2 * 16384, &mx, BAR(MB_FULL + 4), 256, rt * 256);
      uint32_t slot = sb + OFF_X + 3 * 16384;
#pragma unroll 1
      for (int n = 0; n < 11; n++) {
        mbar_wait(BAR(MB_EMPTY) + 8 * n);
        const int m = n + 5;
        e_tma2d(slot, &mx, BAR(MB_FULL) + 8 * m, (m & 7) * 64, rt * 256 + (m >> 3) * 128);
        slot = slot == sb + OFF_X + 4 * 16384 ? sb + OFF_X : slot + 16384;
        if (n == 7) e_prefetch(P.wo + (size_t)b * 2048, 4096);
      }
#pragma unroll 1
      for (int i = 0; i < 8; i++) {
        mbar_wait(BAR(MB_EMPTY + 10) + 8 * ((0x54332100u >> (4 * i)) & 7));
        const int w0 = (0x54736210u >> (4 * i)) & 7;
        e_tma3d(sb + OFF_W + w0 * 16384, &mo, BAR(MB_WO), 0, w0 * 64, (hp & 3) * 2);
      }
    } else {
      if (warp == 15) {
        const uint4 v0 = __ldg((const uint4*)P.wphi + hp * 64 + lane), v1 = __ldg((const uint4*)P.wphi + hp * 64 + 32 + lane);
        sts128(sb + OFF_PHI + (lane & 1) * 256 + (lane >> 1) * 16, v0.x, v0.y, v0.z, v0.w);
        sts128(sb + OFF_PHI + 512 + (lane & 1) * 256 + (lane >> 1) * 16, v1.x, v1.y, v1.z, v1.w);
        asm volatile("fence.proxy.async.shared::cta;" ::: "memory");
        __syncwarp();
        if (lane == 0) mbar_arrive(BAR(MB_AUX));
        mbar_wait(BAR(MB_EMPTY + ZERO_STEP));
        uint4* py = P.xs + X_Y + b * 1024 + lane;
#pragma unroll 1
        for (int i = 0; i < 1024; i += 32) st_x(py + i, 0, 0, 0, 0);
        nb_arrive(NB_YZ, 160);
        nb_arrive(NB_ODONE, 320);
        if (lane == 0) TS1(55);
        return;
      }
      uint32_t* const cnt = (uint32_t*)(P.xs + X_CNT) + (warp == 13 ? i8 : 8 + rt) * 32;
      const unsigned target = (ld_x32(cnt) & ~15u) + 16;
      if (warp == 13) {
        uint4* pp = P.xs + X_PART + (hp * 8 + rt) * 144 + lane;
#pragma unroll 1
        for (int i = 0; i < 144; i += 32) if (i + lane < 144) st_x(pp + i, 0, 0, 0, 0);
      }
      nb_sync(warp == 13 ? NB_INIT : NB_ODONE, warp == 13 ? 160 : 320);
      if (lane == 0) TS1(warp == 13 ? 49 : 56);
      asm volatile("fence.proxy.async.shared::cta;" ::: "memory");
      if (lane == 0) asm volatile("red.release.gpu.global.add.u32 [%0], 1;" ::"l"(cnt) : "memory");
      if (lane == 0) TS1(warp == 13 ? 50 : 57);
      const uint32_t* pc = (warp == 13 && (lane & 1)) ? (uint32_t*)(P.xs + X_CNT) + (b >> 4) * 32 : cnt;
#pragma unroll 1
      for (int i = 0; i < SPIN_MAX; i++) {
        unsigned v;
        asm volatile("ld.acquire.gpu.global.u32 %0, [%1];" : "=r"(v) : "l"(pc) : "memory");
        if (__all_sync(0xffffffffu, (int)(v - target) >= 0)) break;
      }
      if (lane == 0) TS1(warp == 13 ? 51 : 58);
      asm volatile("fence.proxy.async.global;" ::: "memory");
      if (warp == 13) {
        mbar_wait(BAR(MB_EMPTY + 11));
        e_expect(BAR(MB_UFULL), 4 * U_CH);
        e_bulk(sb + OFF_U, P.xs + X_UT + b * (U_CH / 4), 4 * U_CH, BAR(MB_UFULL));
      } else {
        const uint4* src = P.xs + X_O + (rt * 4 + (hp >> 2)) * 4096;
        e_expect(BAR(MB_OA), 14336);
        e_bulk(sb + OFF_STG0, src + 3200, 14336, BAR(MB_OA));
        e_expect(BAR(MB_OC), 32768);
        e_bulk(sb + OFF_X + 32768, src, 32768, BAR(MB_OC));
        nb_sync(NB_BDONE, 288);
        asm volatile("fence.proxy.async.shared::cta;" ::: "memory");
        e_expect(BAR(MB_OB), 18432);
        e_bulk(sb + OFF_U, src + 2048, 18432, BAR(MB_OB));
      }
    }
    return;
  }

  asm volatile("setmaxnreg.inc.sync.aligned.u32 160;");
  const int t = tid & 127;
  const int g = lane >> 2, c = lane & 3;
  {
    if (wg == 2) {
#pragma unroll 1
      for (int q = 0; q < 3; q++) {
        const uint32_t src = q ? tb + (q - 1) * 2608 : sb + OFF_X + 32768 + w * 4096;
#pragma unroll
        for (int j = 0; j < 5; j++) {
          const uint4 v = lds128(src + j * 512 + lane * 16);
          k[j][0] += uf(v.x); k[j][1] += uf(v.y); k[j][2] += uf(v.z); k[j][3] += uf(v.w);
        }
        k2048 += uf(lds32(src + 2560 + (lane & 7) * 4));
        if (q == 0) nb_arrive(NB_KREAD, 160);
      }
#pragma unroll
      for (int o2 = 4; o2; o2 >>= 1) k2048 += __shfl_xor_sync(0xffffffffu, k2048, o2);
      if (lane == 0) k[0][0] += bf_lo(dsk);
      __syncwarp();
      TS(34);
      build_tables(tb, lane, k, k2048);
      TS(35);
      nb_sync(NB_YZ, 160);
      mbar_wait(BAR(MB_UFULL));
      uint4* const g_y = P.xs + X_Y;
      conv_channel(sb + OFF_U + w * U_CH, tb, lane, g_y + (size_t)d * 256 + lane);
      nb_arrive(NB_BDONE, 288);
      TS(37);
      mbar_wait(BAR(MB_OA));
      const int lam = w * 8 + g;
      const uint4* src = g_y + (size_t)(oct * 32 + c * 8) * 256 + i8 * 32 + lam;
      uint4 v[8];
#pragma unroll 1
      for (int it = 0; it < SPIN_MAX; it++) {
        uint32_t m = 0xffffffffu;
#pragma unroll
        for (int i = 0; i < 8; i++) v[i] = ld_x(src + i * 256);
#pragma unroll
        for (int i = 0; i < 8; i++) m = min(m, v[i].x);
        if (__all_sync(0xffffffffu, m != 0)) break;
      }
      __nv_bfloat16* dst = P.out + (size_t)(i8 * 256 + (lam >> 2) * 16 + (lam & 3) * 2) * 1024 + 512 + oct * 32 + c * 8;
#pragma unroll
      for (int i = 0; i < 8; i++) *(uint4*)(dst + (size_t)((i >> 2) * 128 + ((i >> 1) & 1) * 8 + (i & 1)) * 1024) = tr_row(v, i);
      TS(38);
      GT(63);
      return;
    }
    if (wg == 1) {
      mbar_wait(BAR(MB_URAW));
      TS(48);
      uint4* dst = P.xs + X_UT + (i8 * 64 + g) * (U_CH / 16) + (c & 1) * (U_ODD / 16) + U_PAD / 16 + oct * 8 + w * 2 + (c >> 1);
      uint32_t r[8][4];
#pragma unroll
      for (int i = 0; i < 8; i++) ldsm4t(r[i], sb + OFF_STG0 + w * 4096 + lane * 128 + (((i ^ lane) & 7) << 4));
#pragma unroll
      for (int i = 0; i < 8; i++) dst[i * (U_CH / 2)] = make_uint4(r[i][0], r[i][1], r[i][2], r[i][3]);
      nb_arrive(NB_INIT, 160);
      if (lane == 0) mbar_arrive(BAR(MB_AUX));
      mbar_wait(BAR(MB_EMPTY + 6));
    }
    TS(wg * 16 + 1);
  }

  float acc[2][48];
  {
    uint32_t fb = BAR(MB_FULL) + 64 * wg;
    uint32_t da = (uint32_t)mkdesc(sb + OFF_X, 16, 0, 0) + (wg ? 1024 : 3072), db = (uint32_t)mkdesc(sb + OFF_W, 4096, 0, 0);
    constexpr uint64_t ha = mkdesc(0, 0, 1024, 1), hb = mkdesc(0, 0, 512, 2);
#pragma unroll 1
    for (int kb = 0; kb < 8; kb++) {
      mbar_wait(fb);
      if (kb == 0) TS(wg * 16 + 2);
      WG_FENCE();
#pragma unroll
      for (int k = 0; k < 4; k++) {
        wgmma_ss_n96(acc[0], ha | (da + 2 * k), hb | (db + 64 * k), k ? 1 : kb);
        wgmma_ss_n96(acc[1], ha | (da + 2 * k + 512), hb | (db + 64 * k), k ? 1 : kb);
      }
      WG_COMMIT();
      WG_WAIT(1);
      if (kb > 0 && lane == 0) mbar_arrive(fb + 8 * (MB_EMPTY - MB_FULL - 1));
      fb += 8; db += 768;
      da = da == (uint32_t)mkdesc(sb + OFF_X + 65536, 16, 0, 0) ? da - 4096 : da + 1024;
    }
    WG_WAIT(0);
    if (lane == 0) mbar_arrive(fb + 8 * (MB_EMPTY - MB_FULL - 1));
    mbar_wait(fb + 8 * (MB_EMPTY - MB_FULL - 1));
  }
  TS(wg * 16 + 3);

  constexpr uint32_t stg0 = sb + OFF_STG0, stg1 = sb + OFF_X + 32768;
  const uint32_t sl = (wg ? stg1 : stg0) + w * 3072 + lane * 16;
  uint32_t pw[32], eq[32];
  {
    uint4 af[8];
#pragma unroll
    for (int u = 0; u < 8; u++) {
      const float* a = acc[(u >> 1) & 1] + (u < 4 ? 16 : 0) + 8 * (u & 1);
      af[u] = make_uint4(pack_bf(a[0], a[1]), pack_bf(a[2], a[3]), pack_bf(a[4], a[5]), pack_bf(a[6], a[7]));
    }
    mbar_wait(BAR(MB_AUX));
    float p[8][8];
    WG_FENCE();
#pragma unroll
    for (int u = 0; u < 8; u++) wgmma_rs_n16(p[u], af[u], mkdesc(sb + OFF_PHI + (u & 1) * 512, 128, 256, 0), 0);
    WG_COMMIT();
#pragma unroll
    for (int i = 0; i < 4; i++) {
      const float* a = acc[i >> 1] + 32 + 8 * (i & 1);
      stsm4(sl + (i >> 1) * 12288 + 2048 + (i & 1) * 512, pack_bf(a[0], a[1]), pack_bf(a[2], a[3]), pack_bf(a[4], a[5]), pack_bf(a[6], a[7]));
    }
    WG_WAIT(0);
#pragma unroll
    for (int u = 0; u < 8; u++) {
      pw[4 * u] = pack_bf(p[u][0], p[u][2]); pw[4 * u + 1] = pack_bf(p[u][1], p[u][3]);
      pw[4 * u + 2] = pack_bf(p[u][4], p[u][6]); pw[4 * u + 3] = pack_bf(p[u][5], p[u][7]);
    }
  }
  uint32_t ek[32];
  if (wg == 0) {
#pragma unroll
    for (int i = 0; i < 16; i++) { const uint32_t x = pw[i]; pw[i] = pw[16 + i]; pw[16 + i] = x; }
  }
#pragma unroll 1
  for (int it = 0; it < 2; it++) {
#pragma unroll
    for (int i = 0; i < 32; i++) ek[i] = eq[i];
#pragma unroll
    for (int u = 0; u < 4; u++) dual_exp(pw + 4 * u, eq + 8 * u);
    if (it != wg) {
      TS(wg * 16 + 12);
      mbar_wait(BAR(MB_EMPTY + 15));
#pragma unroll
      for (int i = 0; i < 8; i++) norm_store(eq + 4 * i, sl + (i >> 2) * 12288 + (i & 3) * 512);
      if (wg) nb_arrive(NB_ST0, 256);
    }
#pragma unroll
    for (int i = 0; i < 16; i++) pw[i] = pw[i + 16];
  }
  TS(wg * 16 + 4);
  uint4* const g_part = P.xs + X_PART;
  uint4* const g_o = P.xs + X_O;
  const uint32_t kvs = stg0;
  if (wg == 0) {
#pragma unroll
    for (int i = 0; i < 32; i++) eq[i] = ek[i];
    nb_sync(NB_WG0, 128);
    mbar_wait(BAR(MB_UFULL));
    float kv[12], kw[12];
#pragma unroll
    for (int i = 0; i < 12; i++) kv[i] = kw[i] = 0.f;
    const int mi = lane >> 3;
    const uint32_t ao = w * 512 + (lane & 7) * 16 + ((mi & 1) * 2 + (mi >> 1)) * 128, bo = 2048 + (w >> 1) * 512 + lane * 16;
#pragma unroll 1
    for (int j = 0; j < 2; j++) {
      if (j) nb_sync(NB_ST0, 256);
      const uint32_t sg = j ? stg1 : stg0;
      uint32_t a[8][4], bb[8][4];
#pragma unroll
      for (int s = 0; s < 8; s++) { ldsm4t(a[s], sg + s * 3072 + ao); ldsm4t(bb[s], sg + s * 3072 + bo); }
#pragma unroll
      for (int s = 0; s < 8; s++) {
        float* o = (s & 1) ? kw : kv;
        mma(o[0], o[1], o[2], o[3], a[s][0], a[s][1], a[s][2], a[s][3], bb[s][0], bb[s][1]);
        mma(o[4], o[5], o[6], o[7], a[s][0], a[s][1], a[s][2], a[s][3], bb[s][2], bb[s][3]);
        mma(o[8], o[9], o[10], o[11], a[s][0], a[s][1], a[s][2], a[s][3], 0x3F803F80u, 0x3F803F80u);
      }
    }
#pragma unroll
    for (int i = 0; i < 12; i++) kv[i] += kw[i];
    uint4* pp = g_part + (size_t)(hp * 8 + rt) * 144;
    st_x(pp + t, nz(pack_bf(kv[0], kv[1])), pack_bf(kv[2], kv[3]), pack_bf(kv[4], kv[5]), pack_bf(kv[6], kv[7]));
    if (c < 2) st_x32((uint32_t*)(pp + 128) + w * 16 + c * 8 + g, nz(fu(c ? kv[10] : kv[8])));
    TS(5);
    const uint4* ps = g_part + (size_t)hp * 8 * 144 + t;
    const uint32_t* zs = (const uint32_t*)(g_part + (size_t)(hp * 8 + (lane >> 4) * 4) * 144 + 128) + w * 16 + (lane & 15);
    uint4 v[8];
    uint32_t zv[4];
#pragma unroll 1
    for (int it = 0; it < SPIN_MAX; it++) {
#pragma unroll
      for (int i = 0; i < 8; i++) v[i] = ld_x(ps + i * 144);
#pragma unroll
      for (int i = 0; i < 4; i++) zv[i] = ld_x32(zs + i * 576);
      uint32_t m = min(min(zv[0], zv[1]), min(zv[2], zv[3]));
#pragma unroll
      for (int i = 0; i < 8; i++) m = min(m, v[i].x);
      if (__all_sync(0xffffffffu, m != 0)) break;
    }
    float s4[4][4];
#pragma unroll
    for (int i = 0; i < 4; i++) s4[i][0] = s4[i][1] = s4[i][2] = s4[i][3] = 0.f;
    const uint32_t eye = (g >> 1) == c ? ((g & 1) ? 0x3F800000u : 0x3F80u) : 0u;
#pragma unroll
    for (int r = 0; r < 8; r++) {
      mma_k8(s4[(r & 1) * 2], v[r].x, v[r].y, eye);
      mma_k8(s4[(r & 1) * 2 + 1], v[r].z, v[r].w, eye);
    }
    float s[8];
#pragma unroll
    for (int i = 0; i < 8; i++) s[i] = s4[i >> 2][i & 3] + s4[2 + (i >> 2)][i & 3];
    float zsum = (uf(zv[0]) + uf(zv[1])) + (uf(zv[2]) + uf(zv[3]));
    zsum += __shfl_xor_sync(0xffffffffu, zsum, 16);
    stsm4(kvs + w * 512 + lane * 16, pack_bf(s[0], s[1]), pack_bf(s[2], s[3]), pack_bf(s[4], s[5]), pack_bf(s[6], s[7]));
    sts16(kvs + 2048 + (lane >> 4) * 128 + (w * 16 + (lane & 15)) * 2, lane < 16 ? pack_bf(zsum, 0.f) : 0x3F80u);
    TS(6);
  }
  nb_sync(NB_KV, 256);
  {
    uint32_t kb_[4][4], zb[8];
#pragma unroll
    for (int i = 0; i < 4; i++) ldsm4t(kb_[i], kvs + i * 512 + lane * 16);
#pragma unroll
    for (int i = 0; i < 8; i++) zb[i] = lds32(kvs + 2048 + (g & 1) * 128 + i * 16 + c * 4);
    uint32_t* od = (uint32_t*)(g_o + (size_t)((rt * 4 + wg * 2) * 32 + hp * 2) * 128) + w * 64 + lane;
#pragma unroll
    for (int mt = 0; mt < 2; mt++) {
#pragma unroll
      for (int h = 0; h < 2; h++) {
        const uint32_t* e = eq + 16 * mt + 8 * h;
        float n[8], nm[8], dp[4], dm[4];
        mma0(dp[0], dp[1], dp[2], dp[3], e[0], e[1], e[2], e[3], zb[4 * h], zb[4 * h + 1]);
        mma0(dm[0], dm[1], dm[2], dm[3], e[4], e[5], e[6], e[7], zb[4 * h + 2], zb[4 * h + 3]);
        mma0(n[0], n[1], n[2], n[3], e[0], e[1], e[2], e[3], kb_[2 * h][0], kb_[2 * h][1]);
        mma0(nm[0], nm[1], nm[2], nm[3], e[4], e[5], e[6], e[7], kb_[2 * h + 1][0], kb_[2 * h + 1][1]);
        mma0(n[4], n[5], n[6], n[7], e[0], e[1], e[2], e[3], kb_[2 * h][2], kb_[2 * h][3]);
        mma0(nm[4], nm[5], nm[6], nm[7], e[4], e[5], e[6], e[7], kb_[2 * h + 1][2], kb_[2 * h + 1][3]);
        const float q0 = dp[1] * rcp(dm[1]), q1 = dp[3] * rcp(dm[3]);
        const float r0 = rcp(fmaf(dm[0], q0, fmaf(dp[1], 1e-6f, dp[0]))), r1 = rcp(fmaf(dm[2], q1, fmaf(dp[3], 1e-6f, dp[2])));
#pragma unroll
        for (int i = 0; i < 8; i++) n[i] = fmaf(nm[i], (i & 2) ? q1 : q0, n[i]);
        od[h * 512] = pack_bf(n[0] * r0, n[1] * r0);
        od[h * 512 + 32] = pack_bf(n[2] * r1, n[3] * r1);
        od[h * 512 + 256] = pack_bf(n[4] * r0, n[5] * r0);
        od[h * 512 + 288] = pack_bf(n[6] * r1, n[7] * r1);
      }
      od += 16384;
    }
  }
  TS(wg * 16 + 7);
  nb_arrive(NB_ODONE, 320);
  if (wg) return;
  mbar_wait(BAR(MB_WO));
  mbar_wait(BAR(MB_OA));
  TS(8);
  nb_sync(NB_BDONE, 288);
  TS(9);
  float oc[64];
  {
    constexpr uint64_t ha = mkdesc(0, 0, 128, 0), hb = mkdesc(0, 0, 1024, 1);
    constexpr uint32_t da0 = (uint32_t)mkdesc(stg1, 1024, 0, 0), db0 = (uint32_t)mkdesc(sb + OFF_W, 8192, 0, 0);
#pragma unroll 1
    for (int j = 0; j < 8; j++) {
      const int kb = (j + 7) & 7;
      if ((j & 3) == 1) mbar_wait(j == 1 ? BAR(MB_OC) : BAR(MB_OB));
      WG_FENCE();
#pragma unroll
      for (int k = 0; k < 4; k++) wgmma_ss_n128(oc, ha | (da0 + 512 * kb + 128 * k), hb | (db0 + 1024 * kb + 128 * k), k ? 1 : j);
      WG_COMMIT();
    }
    WG_WAIT(0);
  }
  TS(10);
  nb_sync(NB_WG0, 128);
  const uint32_t ot = sb + OFF_W + w * 4096;
#pragma unroll
  for (int i = 0; i < 16; i += 2)
    stsm4(ot + (i >> 3) * 2048 + (lane & 15) * 128 + (((i + (lane >> 4)) ^ lane) & 7) * 16, pack_bf(oc[4 * i], oc[4 * i + 1]),
          pack_bf(oc[4 * i + 2], oc[4 * i + 3]), pack_bf(oc[4 * i + 4], oc[4 * i + 5]), pack_bf(oc[4 * i + 6], oc[4 * i + 7]));
  asm volatile("fence.proxy.async.shared::cta;" ::: "memory");
  __syncwarp();
  e_store3d(&mout, ot, (rt * 4 + (hp >> 2)) * 64 + w * 16, (hp & 3) * 2);
  TS(wg * 16 + 11);
  GT(61 + wg);
}

typedef CUresult (*EncodeFn)(CUtensorMap*, CUtensorMapDataType, cuuint32_t, void*, const cuuint64_t*, const cuuint64_t*,
                             const cuuint32_t*, const cuuint32_t*, CUtensorMapInterleave, CUtensorMapSwizzle,
                             CUtensorMapL2promotion, CUtensorMapFloatOOBfill);

}

extern "C" void kernel_launch(void* const* d_in, const int* in_sizes, int n_in, void* d_out, int out_size) {
  (void)in_sizes; (void)n_in; (void)out_size;
  void* fn = nullptr;
  cudaDriverEntryPointQueryResult qr;
  cudaGetDriverEntryPoint("cuTensorMapEncodeTiled", &fn, cudaEnableDefault, &qr);
  EncodeFn enc = (EncodeFn)fn;
  CUtensorMap mx, mw, mo, mu, mout, mw4;
  const cuuint32_t es[5] = {1, 1, 1, 1, 1};
  {
    cuuint64_t dims[2] = {512, 2048}, st[1] = {1024};
    cuuint32_t box[2] = {64, 128};
    enc(&mx, CU_TENSOR_MAP_DATA_TYPE_BFLOAT16, 2, d_in[0], dims, st, box, es, CU_TENSOR_MAP_INTERLEAVE_NONE,
        CU_TENSOR_MAP_SWIZZLE_128B, CU_TENSOR_MAP_L2_PROMOTION_L2_128B, CU_TENSOR_MAP_FLOAT_OOB_FILL_NONE);
  }
  {
    cuuint64_t dims[3] = {512, 512, 3}, st[2] = {3072, 1024};
    cuuint32_t box[3] = {32, 64, 3};
    enc(&mw, CU_TENSOR_MAP_DATA_TYPE_BFLOAT16, 3, d_in[1], dims, st, box, es, CU_TENSOR_MAP_INTERLEAVE_NONE,
        CU_TENSOR_MAP_SWIZZLE_64B, CU_TENSOR_MAP_L2_PROMOTION_L2_128B, CU_TENSOR_MAP_FLOAT_OOB_FILL_NONE);
  }
  {
    cuuint64_t dims[3] = {64, 512, 8}, st[2] = {1024, 128};
    cuuint32_t box[3] = {64, 64, 2};
    enc(&mo, CU_TENSOR_MAP_DATA_TYPE_BFLOAT16, 3, d_in[3], dims, st, box, es, CU_TENSOR_MAP_INTERLEAVE_NONE,
        CU_TENSOR_MAP_SWIZZLE_128B, CU_TENSOR_MAP_L2_PROMOTION_L2_128B, CU_TENSOR_MAP_FLOAT_OOB_FILL_NONE);
  }
  {
    cuuint64_t dims[5] = {512, 2, 4, 4, 64}, st[4] = {1024, 8192, 2048, 32768};
    cuuint32_t box[5] = {64, 2, 4, 4, 4};
    enc(&mu, CU_TENSOR_MAP_DATA_TYPE_BFLOAT16, 5, d_in[4], dims, st, box, es, CU_TENSOR_MAP_INTERLEAVE_NONE,
        CU_TENSOR_MAP_SWIZZLE_128B, CU_TENSOR_MAP_L2_PROMOTION_L2_128B, CU_TENSOR_MAP_FLOAT_OOB_FILL_NONE);
  }
  {
    cuuint64_t dims[3] = {64, 2048, 16}, st[2] = {2048, 128};
    cuuint32_t box[3] = {64, 16, 2};
    enc(&mout, CU_TENSOR_MAP_DATA_TYPE_BFLOAT16, 3, d_out, dims, st, box, es, CU_TENSOR_MAP_INTERLEAVE_NONE,
        CU_TENSOR_MAP_SWIZZLE_128B, CU_TENSOR_MAP_L2_PROMOTION_NONE, CU_TENSOR_MAP_FLOAT_OOB_FILL_NONE);
  }
  {
    cuuint64_t dims[4] = {512, 64, 3, 8}, st[3] = {3072, 1024, 64 * 3072};
    cuuint32_t box[4] = {32, 64, 3, 4};
    enc(&mw4, CU_TENSOR_MAP_DATA_TYPE_BFLOAT16, 4, d_in[1], dims, st, box, es, CU_TENSOR_MAP_INTERLEAVE_NONE,
        CU_TENSOR_MAP_SWIZZLE_64B, CU_TENSOR_MAP_L2_PROMOTION_L2_128B, CU_TENSOR_MAP_FLOAT_OOB_FILL_NONE);
  }
  Params P;
  P.x = (const __nv_bfloat16*)d_in[0];
  P.wphi = (const __nv_bfloat16*)d_in[2];
  P.wo = (const __nv_bfloat16*)d_in[3];
  P.logA = (const __nv_bfloat16*)d_in[5];
  P.Aim = (const __nv_bfloat16*)d_in[6];
  P.Cre = (const __nv_bfloat16*)d_in[7];
  P.Cim = (const __nv_bfloat16*)d_in[8];
  P.logdt = (const __nv_bfloat16*)d_in[9];
  P.Dskip = (const __nv_bfloat16*)d_in[10];
  P.out = (__nv_bfloat16*)d_out;
  cudaGetSymbolAddress((void**)&P.xs, g_x);
  P.ts = nullptr;
  cudaFuncSetAttribute(fused_kernel, cudaFuncAttributeMaxDynamicSharedMemorySize, SMEM_BYTES);
  fused_kernel<<<NCTA, NTHREADS, SMEM_BYTES>>>(P, mx, mw, mo, mu, mout, mw4);
}
```

```cpp
#include <cuda_runtime.h>
#include <cuda_bf16.h>
#include <cuda_fp16.h>
#include <cuda.h>
#include <stdint.h>

#define DBG_TS 0

namespace {

constexpr int NTHREADS = 512;
constexpr int NCTA = 128;
constexpr int OFF_W = 0;
constexpr int OFF_X = 98304;
constexpr int OFF_U = OFF_X + 65536;
constexpr int U_CH = 4416, U_ODD = 2240, U_PAD = 128;
constexpr int OFF_STG0 = OFF_U + 18432;
constexpr int OFF_T = OFF_STG0 + 24576;
constexpr int T_CH = 5216;
constexpr int T_D = 0;
constexpr int T_5 = 2144;
constexpr int T_3 = T_5 + 384;
constexpr int T_7 = T_5 + 1024;
constexpr int T_9 = T_7 + 320;
constexpr int T_KC = T_9 + 320;
constexpr int T_ST = T_5 - 1024;
constexpr int OFF_PHI = OFF_T + 4 * T_CH;
constexpr int OFF_BAR = OFF_PHI + 1024;
constexpr int SMEM_BYTES = OFF_BAR + 512;
constexpr uint32_t SB = 1024;
static_assert(T_KC + 2 * 656 <= T_CH, "table size");
static_assert(SMEM_BYTES <= 232448, "smem");
constexpr int MB_URAW = 0, MB_FULL = 1  , MB_WO = 17, MB_UFULL = 18, MB_OA = 19, MB_OB = 20, MB_OC = 21,
              MB_EMPTY = 22  , MB_AUX = 38;
__host__ __device__ constexpr uint32_t BAR(int i) { return SB + OFF_BAR + 8 * i; }
constexpr int NB_WG0 = 1, NB_ODONE = 2, NB_ST0 = 3  , NB_KV = 5, NB_YZ = 6, NB_INIT = 7, NB_PREP = 8, NB_PROD = 9, NB_KREAD = 10, NB_BDONE = 11, NB_ZERO = 12;
#define ZERO_STEP 7
constexpr int SPIN_MAX = 1 << 16;

constexpr int X_CNT = 0;
constexpr int X_PART = 128;
constexpr int X_O = X_PART + 16 * 8 * 144;
constexpr int X_Y = X_O + 32 * 32 * 128;
constexpr int X_UT = X_Y + 512 * 8 * 32;
constexpr int X_SIZE = X_UT + 512 * (U_CH / 16);
__device__ __align__(128) uint4 g_x[X_SIZE];
extern __shared__ uint8_t smem_raw[];
#define TS(i) do {} while (0)
#define TS1(i) do {} while (0)
#define GT(i) do {} while (0)

__device__ __forceinline__ uint32_t smem_u32(const void* p) { return (uint32_t)__cvta_generic_to_shared(p); }
__device__ __forceinline__ void mbar_arrive(uint32_t b) {
  asm volatile("mbarrier.arrive.shared::cta.b64 _, [%0];" ::"r"(b) : "memory");
}
__device__ __forceinline__ void mbar_wait(uint32_t b) {
  uint32_t done = 0;
#pragma unroll 1
  for (int i = 0; i < SPIN_MAX && !done; i++) {
    asm volatile("{\n.reg .pred p;\nmbarrier.try_wait.parity.shared::cta.b64 p, [%1], 0, 4000;\nselp.u32 %0, 1, 0, p;\n}\n"
                 : "=r"(done) : "r"(b) : "memory");
  }
}
__device__ __forceinline__ void mbar_init(uint32_t b, int n) {
  asm volatile("mbarrier.init.shared::cta.b64 [%0], %1;" ::"r"(b), "r"(n) : "memory");
}
__device__ __forceinline__ void mbar_expect(uint32_t b, int bytes) {
  asm volatile("mbarrier.arrive.expect_tx.shared::cta.b64 _, [%0], %1;" ::"r"(b), "r"(bytes) : "memory");
}
__device__ __forceinline__ void nb_sync(int id, int n) { asm volatile("bar.sync %0, %1;" ::"r"(id), "r"(n) : "memory"); }
__device__ __forceinline__ void nb_arrive(int id, int n) { asm volatile("bar.arrive %0, %1;" ::"r"(id), "r"(n) : "memory"); }
#define ELECT "{\n.reg .pred p;\nelect.sync _|p, 0xffffffff;\n@p "
__device__ __forceinline__ void e_expect(uint32_t b, int bytes) {
  asm volatile(ELECT "mbarrier.arrive.expect_tx.shared::cta.b64 _, [%0], %1;\n}\n" ::"r"(b), "r"(bytes) : "memory");
}
__device__ __forceinline__ void e_tma2d(uint32_t dst, const CUtensorMap* m, uint32_t bar, int c0, int c1) {
  asm volatile(ELECT "cp.async.bulk.tensor.2d.shared::cluster.global.mbarrier::complete_tx::bytes [%0], [%1, {%3,%4}], [%2];\n}\n"
               ::"r"(dst), "l"(m), "r"(bar), "r"(c0), "r"(c1) : "memory");
}
__device__ __forceinline__ void e_tma3d(uint32_t dst, const CUtensorMap* m, uint32_t bar, int c0, int c1, int c2) {
  asm volatile(ELECT "cp.async.bulk.tensor.3d.shared::cluster.global.mbarrier::complete_tx::bytes [%0], [%1, {%3,%4,%5}], [%2];\n}\n"
               ::"r"(dst), "l"(m), "r"(bar), "r"(c0), "r"(c1), "r"(c2) : "memory");
}
__device__ __forceinline__ void e_tma4d(uint32_t dst, const CUtensorMap* m, uint32_t bar, int c0, int c3) {
  asm volatile(ELECT "cp.async.bulk.tensor.4d.shared::cluster.global.mbarrier::complete_tx::bytes [%0], [%1, {%3,%5,%5,%4}], [%2];\n}\n"
               ::"r"(dst), "l"(m), "r"(bar), "r"(c0), "r"(c3), "r"(0) : "memory");
}
__device__ __forceinline__ void e_tma5d(uint32_t dst, const CUtensorMap* m, uint32_t bar, int c0, int c4) {
  asm volatile(ELECT "cp.async.bulk.tensor.5d.shared::cluster.global.mbarrier::complete_tx::bytes [%0], [%1, {%3,%5,%5,%5,%4}], [%2];\n}\n"
               ::"r"(dst), "l"(m), "r"(bar), "r"(c0), "r"(c4), "r"(0) : "memory");
}
__device__ __forceinline__ void e_bulk(uint32_t dst, const void* src, int bytes, uint32_t bar) {
  asm volatile(ELECT "cp.async.bulk.shared::cluster.global.mbarrier::complete_tx::bytes [%0], [%1], %2, [%3];\n}\n"
               ::"r"(dst), "l"(src), "r"(bytes), "r"(bar) : "memory");
}
__device__ __forceinline__ void e_prefetch(const void* p, int bytes) {
  asm volatile(ELECT "cp.async.bulk.prefetch.L2.global [%0], %1;\n}\n" ::"l"(p), "r"(bytes) : "memory");
}
__device__ __forceinline__ void e_store3d(const CUtensorMap* m, uint32_t src, int c1, int c2) {
  asm volatile(ELECT "cp.async.bulk.tensor.3d.global.shared::cta.bulk_group [%0, {%4,%2,%3}], [%1];\n"
               "@p cp.async.bulk.commit_group;\n@p cp.async.bulk.wait_group.read 0;\n}\n"
               ::"l"(m), "r"(src), "r"(c1), "r"(c2), "r"(0) : "memory");
}
__host__ __device__ constexpr uint64_t mkdesc(uint32_t addr, uint32_t lbo, uint32_t sbo, int swz) {
  return (uint64_t)((addr & 0x3FFFF) >> 4) | ((uint64_t)(lbo >> 4) << 16) | ((uint64_t)(sbo >> 4) << 32) |
         ((uint64_t)swz << 62);
}
#define WG_FENCE() asm volatile("wgmma.fence.sync.aligned;" ::: "memory")
#define WG_COMMIT() asm volatile("wgmma.commit_group.sync.aligned;" ::: "memory")
#define WG_WAIT(n) asm volatile("wgmma.wait_group.sync.aligned " #n ";" ::: "memory")

__device__ __forceinline__ void mma(float& d0, float& d1, float& d2, float& d3, uint32_t a0, uint32_t a1, uint32_t a2,
                                    uint32_t a3, uint32_t b0, uint32_t b1) {
  asm volatile("mma.sync.aligned.m16n8k16.row.col.f32.bf16.bf16.f32 {%0,%1,%2,%3},{%4,%5,%6,%7},{%8,%9},{%0,%1,%2,%3};"
               : "+f"(d0), "+f"(d1), "+f"(d2), "+f"(d3)
               : "r"(a0), "r"(a1), "r"(a2), "r"(a3), "r"(b0), "r"(b1));
}
__device__ __forceinline__ void mmac(float (&d)[4], uint32_t a0, uint32_t a1, uint32_t a2, uint32_t a3, uint32_t b0,
                                     uint32_t b1, const float (&c)[4]) {
  asm volatile("mma.sync.aligned.m16n8k16.row.col.f32.bf16.bf16.f32 {%0,%1,%2,%3},{%4,%5,%6,%7},{%8,%9},{%10,%11,%12,%13};"
               : "=f"(d[0]), "=f"(d[1]), "=f"(d[2]), "=f"(d[3])
               : "r"(a0), "r"(a1), "r"(a2), "r"(a3), "r"(b0), "r"(b1), "f"(c[0]), "f"(c[1]), "f"(c[2]), "f"(c[3]));
}
__device__ __forceinline__ void mma_p(int p, float (&d)[4], uint32_t a0, uint32_t a1, uint32_t a2, uint32_t a3, uint32_t b0, uint32_t b1) {
  asm volatile("{\n.reg .pred q;\nsetp.ne.b32 q, %10, 0;\n"
               "@q mma.sync.aligned.m16n8k16.row.col.f32.bf16.bf16.f32 {%0,%1,%2,%3},{%4,%5,%6,%7},{%8,%9},{%0,%1,%2,%3};\n}\n"
               : "+f"(d[0]), "+f"(d[1]), "+f"(d[2]), "+f"(d[3])
               : "r"(a0), "r"(a1), "r"(a2), "r"(a3), "r"(b0), "r"(b1), "r"(p));
}
__device__ __forceinline__ void mmac_p(int p, float (&d)[4], uint32_t a0, uint32_t a1, uint32_t a2, uint32_t a3, uint32_t b0,
                                       uint32_t b1, const float (&c)[4]) {
  asm volatile("{\n.reg .pred q;\nsetp.ne.b32 q, %14, 0;\n"
               "@q mma.sync.aligned.m16n8k16.row.col.f32.bf16.bf16.f32 {%0,%1,%2,%3},{%4,%5,%6,%7},{%8,%9},{%10,%11,%12,%13};\n}\n"
               : "+f"(d[0]), "+f"(d[1]), "+f"(d[2]), "+f"(d[3])
               : "r"(a0), "r"(a1), "r"(a2), "r"(a3), "r"(b0), "r"(b1), "f"(c[0]), "f"(c[1]), "f"(c[2]), "f"(c[3]), "r"(p));
}
__device__ __forceinline__ void mma_h(float (&d)[4], const uint32_t (&a)[4], uint32_t b0, uint32_t b1) {
  asm volatile("mma.sync.aligned.m16n8k16.row.col.f32.f16.f16.f32 {%0,%1,%2,%3},{%4,%5,%6,%7},{%8,%9},{%0,%1,%2,%3};"
               : "+f"(d[0]), "+f"(d[1]), "+f"(d[2]), "+f"(d[3]) : "r"(a[0]), "r"(a[1]), "r"(a[2]), "r"(a[3]), "r"(b0), "r"(b1));
}
__device__ __forceinline__ void mma_k8(float (&d)[4], uint32_t a0, uint32_t a1, uint32_t b0) {
  asm volatile("mma.sync.aligned.m16n8k8.row.col.f32.bf16.bf16.f32 {%0,%1,%2,%3},{%4,%5},{%6},{%0,%1,%2,%3};"
               : "+f"(d[0]), "+f"(d[1]), "+f"(d[2]), "+f"(d[3]) : "r"(a0), "r"(a1), "r"(b0));
}
__device__ __forceinline__ void mma0(float& d0, float& d1, float& d2, float& d3, uint32_t a0, uint32_t a1, uint32_t a2,
                                     uint32_t a3, uint32_t b0, uint32_t b1) {
  asm volatile("mma.sync.aligned.m16n8k16.row.col.f32.bf16.bf16.f32 {%0,%1,%2,%3},{%4,%5,%6,%7},{%8,%9},{%10,%10,%10,%10};"
               : "=f"(d0), "=f"(d1), "=f"(d2), "=f"(d3)
               : "r"(a0), "r"(a1), "r"(a2), "r"(a3), "r"(b0), "r"(b1), "f"(0.f));
}
__device__ __forceinline__ uint32_t pack_bf(float lo, float hi) {
  uint32_t r;
  asm("cvt.rn.bf16x2.f32 %0, %1, %2;" : "=r"(r) : "f"(hi), "f"(lo));
  return r;
}
__device__ __forceinline__ float bf_lo(uint32_t w) { return __uint_as_float(w << 16); }
__device__ __forceinline__ float bf_hi(uint32_t w) { return __uint_as_float(w & 0xffff0000u); }
__device__ __forceinline__ float bf_round(float x) { return __bfloat162float(__float2bfloat16_rn(x)); }
__device__ __forceinline__ uint32_t bmax2(uint32_t a, uint32_t b) {
  uint32_t r; asm("max.bf16x2 %0, %1, %2;" : "=r"(r) : "r"(a), "r"(b)); return r;
}
__device__ __forceinline__ uint32_t bmin2(uint32_t a, uint32_t b) {
  uint32_t r; asm("min.bf16x2 %0, %1, %2;" : "=r"(r) : "r"(a), "r"(b)); return r;
}
__device__ __forceinline__ float ex2(float x) { float r; asm("ex2.approx.ftz.f32 %0, %1;" : "=f"(r) : "f"(x)); return r; }
__device__ __forceinline__ float rcp(float x) { float r; asm("rcp.approx.ftz.f32 %0, %1;" : "=f"(r) : "f"(x)); return r; }
__device__ __forceinline__ void ldsm4(uint32_t (&r)[4], uint32_t a) {
  asm volatile("ldmatrix.sync.aligned.m8n8.x4.shared.b16 {%0,%1,%2,%3}, [%4];"
               : "=r"(r[0]), "=r"(r[1]), "=r"(r[2]), "=r"(r[3]) : "r"(a) : "memory");
}
__device__ __forceinline__ void ldsm4t(uint32_t (&r)[4], uint32_t a) {
  asm volatile("ldmatrix.sync.aligned.m8n8.x4.trans.shared.b16 {%0,%1,%2,%3}, [%4];"
               : "=r"(r[0]), "=r"(r[1]), "=r"(r[2]), "=r"(r[3]) : "r"(a) : "memory");
}
__device__ __forceinline__ void stsm4(uint32_t a, uint32_t r0, uint32_t r1, uint32_t r2, uint32_t r3) {
  asm volatile("stmatrix.sync.aligned.m8n8.x4.shared.b16 [%0], {%1,%2,%3,%4};"
               ::"r"(a), "r"(r0), "r"(r1), "r"(r2), "r"(r3) : "memory");
}
__device__ __forceinline__ uint32_t lds32(uint32_t a) {
  uint32_t r; asm volatile("ld.shared.u32 %0, [%1];" : "=r"(r) : "r"(a) : "memory"); return r;
}
__device__ __forceinline__ uint32_t lds16(uint32_t a) {
  uint32_t r; asm volatile("{\n.reg .u16 h;\nld.shared.u16 h, [%1];\ncvt.u32.u16 %0, h;\n}\n" : "=r"(r) : "r"(a) : "memory"); return r;
}
__device__ __forceinline__ uint2 lds64(uint32_t a) {
  uint2 r; asm volatile("ld.shared.v2.u32 {%0,%1}, [%2];" : "=r"(r.x), "=r"(r.y) : "r"(a) : "memory"); return r;
}
__device__ __forceinline__ uint4 lds128(uint32_t a) {
  uint4 r;
  asm volatile("ld.shared.v4.u32 {%0,%1,%2,%3}, [%4];" : "=r"(r.x), "=r"(r.y), "=r"(r.z), "=r"(r.w) : "r"(a) : "memory");
  return r;
}
__device__ __forceinline__ void sts32(uint32_t a, uint32_t v) { asm volatile("st.shared.u32 [%0], %1;" ::"r"(a), "r"(v) : "memory"); }
__device__ __forceinline__ void sts16(uint32_t a, uint32_t v) {
  asm volatile("{\n.reg .u16 h;\ncvt.u16.u32 h, %1;\nst.shared.u16 [%0], h;\n}\n" ::"r"(a), "r"(v) : "memory");
}
__device__ __forceinline__ void sts64(uint32_t a, uint32_t x, uint32_t y) {
  asm volatile("st.shared.v2.u32 [%0], {%1,%2};" ::"r"(a), "r"(x), "r"(y) : "memory");
}
__device__ __forceinline__ void sts128(uint32_t a, uint32_t x, uint32_t y, uint32_t z, uint32_t w) {
  asm volatile("st.shared.v4.u32 [%0], {%1,%2,%3,%4};" ::"r"(a), "r"(x), "r"(y), "r"(z), "r"(w) : "memory");
}
__device__ __forceinline__ uint4 ld_x(const uint4* p) {
  uint4 r;
  asm volatile("{\n.reg .b128 t;\nld.relaxed.gpu.global.b128 t, [%4];\nmov.b128 {%0,%1,%2,%3}, t;\n}\n"
               : "=r"(r.x), "=r"(r.y), "=r"(r.z), "=r"(r.w) : "l"(p) : "memory");
  return r;
}
__device__ __forceinline__ uint32_t ld_x32(const uint32_t* p) {
  uint32_t r; asm volatile("ld.relaxed.gpu.global.u32 %0, [%1];" : "=r"(r) : "l"(p) : "memory"); return r;
}
__device__ __forceinline__ void st_x(uint4* p, uint32_t x, uint32_t y, uint32_t z, uint32_t w) {
  asm volatile("{\n.reg .b128 t;\nmov.b128 t, {%1,%2,%3,%4};\nst.relaxed.gpu.global.b128 [%0], t;\n}\n"
               ::"l"(p), "r"(x), "r"(y), "r"(z), "r"(w) : "memory");
}
__device__ __forceinline__ void st_x_p(int p, uint4* a, uint32_t x, uint32_t y, uint32_t z, uint32_t w) {
  asm volatile("{\n.reg .b128 t;\n.reg .pred q;\nsetp.ne.b32 q, %5, 0;\nmov.b128 t, {%1,%2,%3,%4};\n@q st.relaxed.gpu.global.b128 [%0], t;\n}\n"
               ::"l"(a), "r"(x), "r"(y), "r"(z), "r"(w), "r"(p) : "memory");
}
__device__ __forceinline__ void sts64_p(int p, uint32_t a, uint32_t x, uint32_t y) {
  asm volatile("{\n.reg .pred q;\nsetp.ne.b32 q, %3, 0;\n@q st.shared.v2.u32 [%0], {%1,%2};\n}\n" ::"r"(a), "r"(x), "r"(y), "r"(p) : "memory");
}
__device__ __forceinline__ void st_x32(uint32_t* p, uint32_t x) {
  asm volatile("st.relaxed.gpu.global.u32 [%0], %1;" ::"l"(p), "r"(x) : "memory");
}
__device__ __forceinline__ uint32_t nz(uint32_t w) { return max(w, 1u); }
__device__ __forceinline__ uint32_t fu(float x) { return __float_as_uint(x); }
__device__ __forceinline__ float uf(uint32_t x) { return __uint_as_float(x); }

__device__ __forceinline__ void wgmma_ss_n96(float (&d)[48], uint64_t da, uint64_t db, int sc) {
  asm volatile("{\n.reg .pred p;\nsetp.ne.b32 p, %50, 0;\n"
      "wgmma.mma_async.sync.aligned.m64n96k16.f32.bf16.bf16 "
      "{%0,%1,%2,%3,%4,%5,%6,%7,%8,%9,%10,%11,%12,%13,%14,%15,%16,%17,%18,%19,%20,%21,%22,%23,%24,%25,%26,%27,%28,%29,%30,%31,%32,%33,%34,%35,%36,%37,%38,%39,%40,%41,%42,%43,%44,%45,%46,%47}, "
      "%48, %49, p, 1, 1, 0, 1;\n}\n"
      : "+f"(d[0]), "+f"(d[1]), "+f"(d[2]), "+f"(d[3]), "+f"(d[4]), "+f"(d[5]), "+f"(d[6]), "+f"(d[7]),
        "+f"(d[8]), "+f"(d[9]), "+f"(d[10]), "+f"(d[11]), "+f"(d[12]), "+f"(d[13]), "+f"(d[14]), "+f"(d[15]),
        "+f"(d[16]), "+f"(d[17]), "+f"(d[18]), "+f"(d[19]), "+f"(d[20]), "+f"(d[21]), "+f"(d[22]), "+f"(d[23]),
        "+f"(d[24]), "+f"(d[25]), "+f"(d[26]), "+f"(d[27]), "+f"(d[28]), "+f"(d[29]), "+f"(d[30]), "+f"(d[31]),
        "+f"(d[32]), "+f"(d[33]), "+f"(d[34]), "+f"(d[35]), "+f"(d[36]), "+f"(d[37]), "+f"(d[38]), "+f"(d[39]),
        "+f"(d[40]), "+f"(d[41]), "+f"(d[42]), "+f"(d[43]), "+f"(d[44]), "+f"(d[45]), "+f"(d[46]), "+f"(d[47])
      : "l"(da), "l"(db), "r"(sc));
}

__device__ __forceinline__ void wgmma_ss_n128(float (&d)[64], uint64_t da, uint64_t db, int sc) {
  asm volatile("{\n.reg .pred p;\nsetp.ne.b32 p, %66, 0;\n"
      "wgmma.mma_async.sync.aligned.m64n128k16.f32.bf16.bf16 "
      "{%0,%1,%2,%3,%4,%5,%6,%7,%8,%9,%10,%11,%12,%13,%14,%15,%16,%17,%18,%19,%20,%21,%22,%23,%24,%25,%26,%27,%28,%29,%30,%31,%32,%33,%34,%35,%36,%37,%38,%39,%40,%41,%42,%43,%44,%45,%46,%47,%48,%49,%50,%51,%52,%53,%54,%55,%56,%57,%58,%59,%60,%61,%62,%63}, "
      "%64, %65, p, 1, 1, 0, 1;\n}\n"
      : "+f"(d[0]), "+f"(d[1]), "+f"(d[2]), "+f"(d[3]), "+f"(d[4]), "+f"(d[5]), "+f"(d[6]), "+f"(d[7]),
        "+f"(d[8]), "+f"(d[9]), "+f"(d[10]), "+f"(d[11]), "+f"(d[12]), "+f"(d[13]), "+f"(d[14]), "+f"(d[15]),
        "+f"(d[16]), "+f"(d[17]), "+f"(d[18]), "+f"(d[19]), "+f"(d[20]), "+f"(d[21]), "+f"(d[22]), "+f"(d[23]),
        "+f"(d[24]), "+f"(d[25]), "+f"(d[26]), "+f"(d[27]), "+f"(d[28]), "+f"(d[29]), "+f"(d[30]), "+f"(d[31]),
        "+f"(d[32]), "+f"(d[33]), "+f"(d[34]), "+f"(d[35]), "+f"(d[36]), "+f"(d[37]), "+f"(d[38]), "+f"(d[39]),
        "+f"(d[40]), "+f"(d[41]), "+f"(d[42]), "+f"(d[43]), "+f"(d[44]), "+f"(d[45]), "+f"(d[46]), "+f"(d[47]),
        "+f"(d[48]), "+f"(d[49]), "+f"(d[50]), "+f"(d[51]), "+f"(d[52]), "+f"(d[53]), "+f"(d[54]), "+f"(d[55]),
        "+f"(d[56]), "+f"(d[57]), "+f"(d[58]), "+f"(d[59]), "+f"(d[60]), "+f"(d[61]), "+f"(d[62]), "+f"(d[63])
      : "l"(da), "l"(db), "r"(sc));
}

__device__ __forceinline__ void wgmma_rs_n16(float (&d)[8], const uint4& a, uint64_t db, int sc) {
  asm volatile("{\n.reg .pred p;\nsetp.ne.b32 p, %13, 0;\n"
      "wgmma.mma_async.sync.aligned.m64n16k16.f32.bf16.bf16 "
      "{%0,%1,%2,%3,%4,%5,%6,%7}, "
      "{%8,%9,%10,%11}, %12, p, 1, 1, 1;\n}\n"
      : "+f"(d[0]), "+f"(d[1]), "+f"(d[2]), "+f"(d[3]), "+f"(d[4]), "+f"(d[5]), "+f"(d[6]), "+f"(d[7])
      : "r"(a.x), "r"(a.y), "r"(a.z), "r"(a.w), "l"(db), "r"(sc));
}

struct Params {
  const __nv_bfloat16 *logA, *Aim, *Cre, *Cim, *logdt, *Dskip, *x, *wphi, *wo;
  __nv_bfloat16* out;
  uint4* xs;
  long long* ts;
};

__device__ __forceinline__ uint4 tr_row(const uint4 (&v)[8], int i) {
  uint32_t o[4];
#pragma unroll
  for (int m = 0; m < 4; m++) {
    const uint4 &ra = v[2 * m], &rb = v[2 * m + 1];
    const int k = i >> 1;
    const uint32_t xa = k == 0 ? ra.x : k == 1 ? ra.y : k == 2 ? ra.z : ra.w;
    const uint32_t xb = k == 0 ? rb.x : k == 1 ? rb.y : k == 2 ? rb.z : rb.w;
    o[m] = __byte_perm(xa, xb, (i & 1) ? 0x7632 : 0x5410);
  }
  return make_uint4(o[0], o[1], o[2], o[3]);
}

struct cpx { float r, i; };
__device__ __forceinline__ cpx csq(cpx a) { return {a.r * a.r - a.i * a.i, 2.f * (a.r * a.i)}; }
__device__ __forceinline__ cpx polar(float e, float t) {
  const float m = ex2(e);
  return {m * __cosf(t), m * __sinf(t)};
}

struct KgenRaw { unsigned short la, ai, cr, ci, ldt; };
__device__ __forceinline__ KgenRaw kgen_load(const Params& P, int d, int unit, int lane) {
  const int o = d * 128 + unit * 32 + lane;
  return {__ldg((const unsigned short*)P.logA + o), __ldg((const unsigned short*)P.Aim + o), __ldg((const unsigned short*)P.Cre + o),
          __ldg((const unsigned short*)P.Cim + o), __ldg((const unsigned short*)P.logdt + d)};
}
struct hmul { __half2 a, b; };
__device__ __forceinline__ hmul mk_mul(cpx w) { return {__floats2half2_rn(w.r, w.i), __floats2half2_rn(-w.i, w.r)}; }
__device__ __forceinline__ __half2 hcm(__half2 z, const hmul& w) { return __hfma2(__high2half2(z), w.b, __hmul2(__low2half2(z), w.a)); }
__device__ __forceinline__ uint32_t hu(__half2 v) { return *(const uint32_t*)&v; }

__device__ __forceinline__ void kgen_unit(const KgenRaw& r, int lane, uint32_t buf, uint32_t zero, float (&k)[5][4], float& k2048) {
  const float dt = bf_round(expf(bf_lo(r.ldt)));
  const float a2 = -(bf_round(expf(bf_lo(r.la))) * dt) * 1.4426950408889634f;
  const float f = bf_lo(r.ai) * dt;
  const float r128 = f * 20.371832715762604f;
  const uint32_t ex = min(max(__reduce_max_sync(0xffffffffu, max(r.cr & 0x7fffu, r.ci & 0x7fffu)) >> 7, 1u), 253u);
  const float cs = uf((254u - ex) << 23), sc = 2.f * dt * uf(ex << 23);
  const cpx C = {bf_lo(r.cr) * cs, -bf_lo(r.ci) * cs};
  const uint32_t sa = buf + (lane & 7) * 128 + ((((lane >> 3) ^ lane) & 7) << 4);
  const uint32_t lb = buf + (lane >> 3) * 128 + (((lane ^ (lane >> 3)) & 7) << 4);
  const uint32_t la = buf + ((lane >> 3) & 1) * 1024 + (lane >> 4) * 128 + (((lane ^ (lane >> 4)) & 7) << 4);
  auto put = [&](const __half2 (&v)[8], uint32_t off) {
    stsm4(sa + off, hu(v[0]), hu(v[1]), hu(v[2]), hu(v[3]));
    stsm4((sa ^ 64) + off, hu(v[4]), hu(v[5]), hu(v[6]), hu(v[7]));
  };
  uint32_t A[4][4], B[5][2][4];
  auto get = [&](int j, uint32_t off) {
    __syncwarp();
    ldsm4(B[j][0], lb + off);
    ldsm4(B[j][1], (lb ^ 64) + 512 + off);
  };
  auto tile = [&](int j) {
    k[j][0] = k[j][1] = k[j][2] = k[j][3] = 0.f;
#pragma unroll
    for (int s = 0; s < 4; s++) mma_h(k[j], A[s], B[j][s >> 1][2 * (s & 1)], B[j][s >> 1][2 * (s & 1) + 1]);
  };
  auto after = [&](cpx v, uint32_t dep) { return cpx{uf(fu(v.r) ^ (dep & zero)), v.i}; };
  const cpx w1 = polar(a2, f), w128 = polar(a2 * 128.f, (r128 - rintf(r128)) * 6.283185307179586f);
  const cpx w2 = csq(w1), w4 = csq(w2);
  __half2 t0[8], t1[8], t2[8], t3[8], t4[8];
  const hmul m2 = mk_mul(w2), m4 = mk_mul(w4), m128 = mk_mul(w128);
  t0[0] = __floats2half2_rn(1.f, 0.f); t0[1] = __floats2half2_rn(w1.r, w1.i); t0[2] = m2.a; t0[4] = m4.a;
  t0[3] = hcm(t0[1], m2); t0[5] = hcm(t0[1], m4); t0[6] = hcm(t0[2], m4); t0[7] = hcm(t0[3], m4);
  put(t0, 0); get(0, 0);
  t1[0] = m128.a;
#pragma unroll
  for (int i = 1; i < 8; i++) t1[i] = hcm(t0[i], m128);
  put(t1, 1024); get(1, 1024);
  {
    cpx w8 = csq(after(w4, B[0][0][0]));
    w8.i = -w8.i;
    const cpx w16 = csq(w8), w32 = csq(w16), w64 = csq(w32);
    const hmul m8 = mk_mul(w8), m16 = mk_mul(w16), m32 = mk_mul(w32), m64 = mk_mul(w64);
    __half2 a[8];
    a[0] = __floats2half2_rn(C.r, C.i); a[1] = hcm(a[0], m8);
    a[2] = hcm(a[0], m16); a[3] = hcm(a[1], m16);
#pragma unroll
    for (int i = 0; i < 4; i++) a[4 + i] = hcm(a[i], m32);
    put(a, 0);
#pragma unroll
    for (int i = 0; i < 8; i++) a[i] = hcm(a[i], m64);
    put(a, 1024);
    __syncwarp();
#pragma unroll
    for (int s = 0; s < 4; s++) ldsm4(A[s], (la ^ (s << 5)) + s * 256);
  }
  const cpx w256 = csq(after(w128, B[1][0][0]));
  const hmul m256 = mk_mul(w256);
  t2[0] = m256.a;
#pragma unroll
  for (int i = 1; i < 8; i++) t2[i] = hcm((i & 1) ? t1[i & 6] : t0[i & 6], m256);
  put(t2, 0); get(2, 0);
  tile(0); tile(1);
  const cpx w512 = csq(after(w256, A[0][0]));
  const hmul m512 = mk_mul(w512);
  t3[0] = m512.a;
#pragma unroll
  for (int i = 1; i < 8; i++) t3[i] = hcm((i & 2) ? t2[i & 5] : ((i & 1) ? t1[i & 4] : t0[i & 4]), m512);
  put(t3, 1024); get(3, 1024);
  tile(2);
  const cpx w1024 = csq(after(w512, B[2][0][0])), we = csq(w1024);
  const hmul m1024 = mk_mul(w1024);
  t4[0] = m1024.a;
#pragma unroll
  for (int i = 1; i < 8; i++) t4[i] = hcm((i & 4) ? t3[i & 3] : ((i & 2) ? t2[i & 1] : t1[0]), m1024);
  put(t4, 0); get(4, 0);
  tile(3); tile(4);
  k2048 = (C.r * we.r + C.i * we.i) * sc;
#pragma unroll
  for (int j = 0; j < 5; j++) { k[j][0] *= sc; k[j][1] *= sc; k[j][2] *= sc; k[j][3] *= sc; }
}

__device__ __forceinline__ void build_tables(uint32_t tb, int lane, float (&k)[5][4], float k2048) {
  const int g = lane >> 2, c = lane & 3;
  const uint32_t kc = tb + T_KC + 16;
  {
    const uint32_t a0 = kc + 16 * g + 4 * c, a2 = kc + 2 * (256 + 4 * g + c);
    const uint32_t a3 = kc + 2 * (384 + 2 * g + 64 * (c & 1) + (c >> 1)), a4 = kc + 2 * (512 + g + 32 * c);
#pragma unroll
    for (int r = 0; r < 2; r++) {
      sts32(a0 + 128 * r, pack_bf(k[0][2 * r], k[0][2 * r + 1]));
      sts32(a0 + 128 * r + 256, pack_bf(k[1][2 * r], k[1][2 * r + 1]));
      const uint32_t w2 = pack_bf(k[2][2 * r], k[2][2 * r + 1]);
      const uint32_t w3 = pack_bf(k[3][2 * r], k[3][2 * r + 1]);
      const uint32_t w4 = pack_bf(k[4][2 * r], k[4][2 * r + 1]);
      sts16(a2 + 64 * r, w2); sts16(a2 + 64 * r + 128, w2 >> 16);
      sts16(a3 + 32 * r, w3); sts16(a3 + 32 * r + 64, w3 >> 16);
      sts16(a4 + 16 * r, w4); sts16(a4 + 16 * r + 32, w4 >> 16);
    }
  }
  if (lane == 0) { sts16(kc + 2 * 640, pack_bf(k2048, 0.f)); sts16(kc - 2, 0); }
  __syncwarp();
  const uint32_t td = tb + T_D + 32;
  {
    const uint4 v = lds128(kc + 16 * lane);
    const uint32_t pv = lds16(kc + 16 * lane - 2);
    sts128(td + 32 * lane, __byte_perm(v.x, pv, 0x5410), __byte_perm(v.x, v.x, 0x1032), __byte_perm(v.y, v.x, 0x7610),
           __byte_perm(v.y, v.y, 0x1032));
    sts128(td + 32 * lane + 16, __byte_perm(v.z, v.y, 0x7610), __byte_perm(v.z, v.z, 0x1032),
           __byte_perm(v.w, v.z, 0x7610), __byte_perm(v.w, v.w, 0x1032));
  }
  {
    const uint2 v = lds64(kc + 512 + 8 * lane);
    const uint32_t k4 = lds16(kc + 512 + 8 * lane + 8);
    const uint32_t pv = lds16(kc + (lane == 0 ? 510 : 512 + 8 * lane));
    const uint32_t k22 = __byte_perm(v.y, v.y, 0x1010);
    sts128(td + 1024 + 32 * lane, __byte_perm(v.x, pv, 0x5410), __byte_perm(v.x, v.x, 0x1010),
           __byte_perm(v.x, v.x, 0x1032), __byte_perm(v.y, v.x, 0x7610));
    sts128(td + 1024 + 32 * lane + 16, k22, k22, __byte_perm(v.y, v.y, 0x1032), __byte_perm(k4, v.y, 0x7610));
  }
  {
    const uint32_t kk = lds16(kc + 2 * 384);
    const uint32_t w = lane < 3 ? (kk | (kk << 16)) : (lane == 3 ? (kk << 16) : 0u);
    if (lane < 24) sts32(td + 4 * (lane < 16 ? 512 + lane : lane - 24), w);
    const uint32_t lo_ = lds16(kc + 2 * 511), le_ = lds16(kc + 2 * 512);
    const uint32_t ja = tb + T_5 + (lane < 16 ? 4 * lane : 256 + 4 * lane);
    sts32(ja, lane == 16 ? (le_ << 16) : 0u);
    sts32(ja + 384, lane == 16 ? (lo_ << 16) : 0u);
    sts32(tb + (lane < 16 ? T_7 : T_9 - 64) + 4 * lane, 0u);
  }
#pragma unroll
  for (int s = 0; s < 2; s++) {
    const uint32_t b = kc + 2 * (s ? 512 : 384) + 8 * lane;
    const uint2 v = lds64(b);
    uint32_t em = lds16(b - 2), e0 = v.x;
    const uint32_t e4 = lds16(b + 8);
    if (lane == 0) { em = 0; e0 = 0; }
    sts64(tb + (s ? T_7 : T_3) + 64 + 8 * lane, __byte_perm(v.x, em, 0x5432), __byte_perm(v.y, v.x, 0x7632));
    sts64(tb + (s ? T_9 : T_5) + 64 + 8 * lane, __byte_perm(v.y, e0, 0x5410), __byte_perm(e4, v.y, 0x5410));
  }
  __syncwarp();
}

__device__ __forceinline__ uint32_t box2w(int lo, int n, int o) {
  return ((unsigned)(o - lo) < (unsigned)n ? 0x3F80u : 0u) | ((unsigned)(o + 1 - lo) < (unsigned)n ? 0x3F800000u : 0u);
}

#define SPLIT() asm volatile("{\n.reg .pred p;\nsetp.ne.u32 p, %0, 0;\n@p exit;\n}\n" ::"r"(blockIdx.y) : "memory")

__device__ __forceinline__ void conv_channel(uint32_t ub, uint32_t tb, int lane, uint4* ydst) {
  const int g = lane >> 2, c = lane & 3, x = g - 2 * c;
  const int mi = lane >> 3;
  const uint32_t qa = ub + U_PAD + 16 * (lane & 7) + ((mi == 0 || mi == 3) ? U_ODD : 0) - (mi == 0 ? 16 : 0);
  const uint32_t hb = ub + U_PAD + (mi & 1) * U_ODD + 16 * ((lane >> 4) + (lane & 7)) - 16;
  const uint32_t kv = lds16(tb + T_KC + 16 + 2 * 512);
  const int oh = c < 2 ? 8 + 2 * c : 2 * c - 8, og = c < 3 ? 2 * c : -10;
  uint32_t bx[4] = {box2w(g - 4, 9, 2 * c), box2w(g - 3, 7, 2 * c), box2w(g - 4, 9, oh), box2w(g - 3, 7, oh)};
  uint32_t by[4] = {box2w(g - 10, 5, 2 * c - 8), box2w(g - 5, 3, 2 * c - 8), box2w(g - 10, 5, og), box2w(g - 5, 3, og)};
  uint32_t lb0 = ((unsigned)(x + 5) < 2u ? kv : 0u) | ((unsigned)(x + 4) < 2u ? kv << 16 : 0u);
  uint32_t lb1 = ((unsigned)(x - 3) < 2u ? kv : 0u) | ((unsigned)(x - 4) < 2u ? kv << 16 : 0u);
  const int q0 = g - 1, q1 = c < 3 ? g : g - 2;
  uint32_t y0a = ub + U_PAD + (q0 & 1) * U_ODD + 16 * (q0 >> 1) + 4 * c;
  uint32_t y1a = ub + U_PAD + (q1 & 1) * U_ODD + 16 * (q1 >> 1) + 4 * c;
  uint32_t f3[3][4][4];
  {
    const uint32_t fa = tb + T_7 + 4 * (16 + x);
#pragma unroll
    for (int tt = 0; tt < 3; tt++)
#pragma unroll
      for (int D = 0; D < 4; D++) {
        const uint32_t a = fa + (tt == 0 ? 316 : (tt == 1 ? 320 : 0)) + 64 * D;
        f3[tt][D][0] = lds32(a); f3[tt][D][1] = lds32(a + 32); f3[tt][D][2] = lds32(a - 32); f3[tt][D][3] = lds32(a);
      }
  }
#pragma unroll
  for (int i = 0; i < 4; i++) asm volatile("" : "+r"(bx[i]), "+r"(by[i]));
  asm volatile("" : "+r"(lb0), "+r"(lb1), "+r"(y0a), "+r"(y1a));
  mbar_wait(BAR(MB_UFULL));
  mbar_wait(BAR(MB_EMPTY + 15));
  TS(36);
  float acc[16][4];
  {
    uint32_t z09[8], z07[8], zm9[8], zm7[8];
#pragma unroll
    for (int i = 0; i < 8; i++) {
      uint32_t h[4];
      ldsm4(h, hb + 128 * i);
      float y0, y1, y2, y3, w0, w1, w2, w3;
      mma0(y0, y1, y2, y3, bx[0], bx[1], bx[2], bx[3], h[2], c < 2 ? h[3] : h[1]);
      mma0(w0, w1, w2, w3, bx[0], bx[1], bx[2], bx[3], h[1], c < 2 ? h[2] : h[0]);
      z09[i] = pack_bf(y0, y1); z07[i] = pack_bf(y2, y3);
      zm9[i] = pack_bf(w0, w1); zm7[i] = pack_bf(w2, w3);
    }
    float a[4][2][4];
#pragma unroll
    for (int kap = 0; kap < 4; kap++)
#pragma unroll
      for (int sg = 0; sg < 2; sg++)
#pragma unroll
        for (int bk = 3; bk >= kap; bk--) {
          const uint32_t(&q0_)[4] = f3[sg ? 2 : 0][bk - kap];
          const uint32_t(&q1_)[4] = f3[sg ? 2 : 1][bk - kap];
          float(&a0)[4] = a[bk][0];
          float(&a1)[4] = a[bk][1];
          if (sg == 0 && kap == 0) {
            mma0(a0[0], a0[1], a0[2], a0[3], q0_[0], q0_[1], q0_[2], q0_[3], z09[0], z09[1]);
            mma0(a1[0], a1[1], a1[2], a1[3], q1_[0], q1_[1], q1_[2], q1_[3], zm9[0], zm9[1]);
          } else {
            mma(a0[0], a0[1], a0[2], a0[3], q0_[0], q0_[1], q0_[2], q0_[3], sg ? zm7[2 * kap] : z09[2 * kap], sg ? zm7[2 * kap + 1] : z09[2 * kap + 1]);
            mma(a1[0], a1[1], a1[2], a1[3], q1_[0], q1_[1], q1_[2], q1_[3], sg ? z07[2 * kap] : zm9[2 * kap], sg ? z07[2 * kap + 1] : zm9[2 * kap + 1]);
          }
        }
    SPLIT();
#pragma unroll
    for (int i = 0; i < 8; i++) {
      uint32_t h[4];
      ldsm4(h, qa + 128 * i);
      const float ci[4] = {a[i >> 1][0][2 * (i & 1)], a[i >> 1][0][2 * (i & 1) + 1], a[i >> 1][1][2 * (i & 1)], a[i >> 1][1][2 * (i & 1) + 1]};
      mmac(acc[8 + i], h[0], h[1], h[2], h[3], lb0, lb1, ci);
    }
  }
  TS(44);
  {
    uint2 a5[10], a3[10];
    const uint32_t aa = tb + T_5 + 4 * (8 + 2 * g - 2 * c);
#pragma unroll
    for (int m = 0; m < 10; m++) { a5[m] = lds64(aa + 32 * m); a3[m] = lds64(aa + 384 + 32 * m); }
    uint32_t x5[12][2], x3[12][2];
    auto ygen = [&](int kap) {
#pragma unroll
      for (int hh = 0; hh < 2; hh++) {
        float y0, y1, y2, y3;
        mma0(y0, y1, y2, y3, by[0], by[1], by[2], by[3], lds32(y0a + 128 * kap + 64 * hh), lds32(y1a + 128 * kap + 64 * hh));
        x5[kap][hh] = pack_bf(y0, y1);
        x3[kap][hh] = pack_bf(y2, y3);
      }
    };
    ygen(11); ygen(10); ygen(9); ygen(8);
#pragma unroll
    for (int kap = 11; kap >= 0; kap--) {
      if (kap >= 4) ygen(kap - 4);
#pragma unroll
      for (int sg = 0; sg < 2; sg++)
#pragma unroll
        for (int i = 4; i >= 0; i--) {
          const int be = kap + 4 + i;
          if (be <= 15) {
            const uint2 &hi = sg ? a3[2 * i + 1] : a5[2 * i + 1], &lo = sg ? a3[2 * i] : a5[2 * i];
            const uint32_t b0 = sg ? x3[kap][0] : x5[kap][0], b1 = sg ? x3[kap][1] : x5[kap][1];
            if (be < 8 && i == 0 && sg == 0) mma0(acc[be][0], acc[be][1], acc[be][2], acc[be][3], hi.x, hi.y, lo.x, lo.y, b0, b1);
            else mma(acc[be][0], acc[be][1], acc[be][2], acc[be][3], hi.x, hi.y, lo.x, lo.y, b0, b1);
          }
        }
    }
  }
  TS(45);
  {
    const uint32_t st = tb + T_ST + lane * 8;
#pragma unroll
    for (int be = 4; be < 12; be++) sts64(st + 256 * be, pack_bf(acc[be][0], acc[be][1]), pack_bf(acc[be][2], acc[be][3]));
    SPLIT();
    uint32_t F[66], qd[8][4];
    const uint32_t fa = tb + T_D + 32 + 4 * x;
#pragma unroll
    for (int i = 0; i < 32; i++) {
      const int s = 120 - (i >> 2) - 8 * (i & 3);
      uint32_t(&q)[4] = qd[i & 7];
      ldsm4(q, qa + 16 * s);
      const int m = 16 * (i & 3) + 2 * (i >> 2);
      F[m] = lds32(fa + 32 * m); F[m + 1] = lds32(fa + 32 * m + 32);
#pragma unroll
      for (int be = 15; be >= 12; be--) {
        const int de = 8 * be - s;
        if (de >= 0) mma(acc[be][0], acc[be][1], acc[be][2], acc[be][3], q[0], q[1], q[2], q[3], F[2 * de + 1], F[2 * de]);
      }
    }
    F[64] = lds32(fa + 32 * 64); F[65] = lds32(fa + 32 * 65);
    uint32_t qp = qa + 128 * 11, sta = st + 256 * 10;
    uint4* yd = ydst + 7 * 32;
#pragma unroll
    for (int i = 0; i < 6; i++) ldsm4(qd[i], qp - 16 * i);
    uint2 sv = lds64(sta + 256);
    float ci[4] = {bf_lo(sv.x), bf_hi(sv.x), bf_lo(sv.y), bf_hi(sv.y)};
    float T[5][4];
#pragma unroll
    for (int i = 0; i < 16; i++) T[i >> 2][i & 3] = acc[12 + (i >> 2)][i & 3];
    TS(46);
#pragma unroll 1
    for (int bp = 5; bp >= 0; bp--) {
      uint32_t held[2];
#pragma unroll
      for (int o = 1; o >= 0; o--) {
#pragma unroll
        for (int k = 4; k >= 1; k--) mmac(T[k], qd[0][0], qd[0][1], qd[0][2], qd[0][3], F[16 * k + 1], F[16 * k], T[k - 1]);
        mmac(T[0], qd[0][0], qd[0][1], qd[0][2], qd[0][3], F[1], F[0], ci);
        ldsm4(qd[6], qp - 16 * 6);
        ldsm4(qd[7], qp - 16 * 7);
        sv = lds64(sta);
#pragma unroll
        for (int i = 1; i < 8; i++) {
#pragma unroll
          for (int k = 3; k >= 0; k--)
            mma(T[k][0], T[k][1], T[k][2], T[k][3], qd[i][0], qd[i][1], qd[i][2], qd[i][3], F[16 * k + 2 * i + 1], F[16 * k + 2 * i]);
          if (i < 7) ldsm4(qd[i - 1], qp - 128 - 16 * (i - 1));
          if (i == 2) {
            const uint32_t w0 = pack_bf(T[4][0], T[4][1]), w1 = pack_bf(T[4][2], T[4][3]);
            if (o) { held[0] = w0; held[1] = w1; }
            else st_x(yd, nz(w0), w1, held[0], held[1]);
          }
          if (i == 4) {
            if (2 * bp + o <= 4) sv = make_uint2(0, 0);
            ci[0] = bf_lo(sv.x); ci[1] = bf_hi(sv.x); ci[2] = bf_lo(sv.y); ci[3] = bf_hi(sv.y);
          }
        }
        qp -= 128; sta -= 256;
      }
      yd -= 32;
    }
#pragma unroll
    for (int B = 1; B >= 0; B--)
      st_x(ydst + B * 32, nz(pack_bf(T[2 * B][0], T[2 * B][1])), pack_bf(T[2 * B][2], T[2 * B][3]),
           pack_bf(T[2 * B + 1][0], T[2 * B + 1][1]), pack_bf(T[2 * B + 1][2], T[2 * B + 1][3]));
  }
}

__device__ __forceinline__ void dual_exp(const uint32_t* w, uint32_t* e) {
  const float L = 1.44268798828125f;
  uint32_t mx = bmax2(bmax2(w[0], w[1]), bmax2(w[2], w[3]));
  uint32_t mn = bmin2(bmin2(w[0], w[1]), bmin2(w[2], w[3]));
  mx = bmax2(mx, __shfl_xor_sync(0xffffffffu, mx, 1));
  mn = bmin2(mn, __shfl_xor_sync(0xffffffffu, mn, 1));
  mx = bmax2(mx, __shfl_xor_sync(0xffffffffu, mx, 2));
  mn = bmin2(mn, __shfl_xor_sync(0xffffffffu, mn, 2));
  const float mx0 = bf_lo(mx) * -L, mx1 = bf_hi(mx) * -L, mn0 = bf_lo(mn) * L, mn1 = bf_hi(mn) * L;
#pragma unroll
  for (int i = 0; i < 2; i++) {
    const float a0 = bf_lo(w[2 * i]), a1 = bf_hi(w[2 * i]), b0 = bf_lo(w[2 * i + 1]), b1 = bf_hi(w[2 * i + 1]);
    e[2 * i] = pack_bf(ex2(fmaf(a0, L, mx0)), ex2(fmaf(b0, L, mx0)));
    e[2 * i + 1] = pack_bf(ex2(fmaf(a1, L, mx1)), ex2(fmaf(b1, L, mx1)));
    e[4 + 2 * i] = pack_bf(ex2(fmaf(a0, -L, mn0)), ex2(fmaf(b0, -L, mn0)));
    e[5 + 2 * i] = pack_bf(ex2(fmaf(a1, -L, mn1)), ex2(fmaf(b1, -L, mn1)));
  }
}
__device__ __forceinline__ void norm_store(const uint32_t* e, uint32_t dst) {
  float s[4];
  mma0(s[0], s[1], s[2], s[3], e[0], e[1], e[2], e[3], 0x3F803F80u, 0x3F803F80u);
  const uint32_t r = pack_bf(rcp(s[0]), rcp(s[2]));
  const __nv_bfloat162 rr = *(const __nv_bfloat162*)&r;
  uint32_t o[4];
#pragma unroll
  for (int i = 0; i < 4; i++) {
    const __nv_bfloat162 v = __hmul2(*(const __nv_bfloat162*)&e[i], (i & 1) ? __high2bfloat162(rr) : __low2bfloat162(rr));
    o[i] = *(const uint32_t*)&v;
  }
  stsm4(dst, o[0], o[1], o[2], o[3]);
}

__global__ void __launch_bounds__(NTHREADS, 1)
fused_kernel(const Params P, const __grid_constant__ CUtensorMap mx, const __grid_constant__ CUtensorMap mw,
             const __grid_constant__ CUtensorMap mo, const __grid_constant__ CUtensorMap mu,
             const __grid_constant__ CUtensorMap mout, const __grid_constant__ CUtensorMap mw4) {
  constexpr uint32_t sb = SB;
  const int tid = threadIdx.x, lane = tid & 31;
  const int warp = __shfl_sync(0xffffffffu, tid >> 5, 0);
  const int b = blockIdx.x, oct = b >> 3, i8 = b & 7;
  const int rt = oct < 8 ? oct : 15 - oct;
  const int hp = (oct >> 3) * 8 + i8;

  const int wg = warp >> 2, w = warp & 3;
  const int d = b * 4 + ((tid >> 5) & 3);
  if (tid < 384) {
    asm volatile("prefetch.tensormap [%0];" ::"l"(&mu) : "memory");
    asm volatile("prefetch.tensormap [%0];" ::"l"(&mw) : "memory");
    asm volatile("prefetch.tensormap [%0];" ::"l"(&mx) : "memory");
    asm volatile("prefetch.tensormap [%0];" ::"l"(&mw4) : "memory");
  }
  if (warp == 12) {
    if (lane == 0) {
#pragma unroll
      for (int i = 0; i < 9; i++) mbar_init(BAR(i), 1);
      asm volatile("fence.mbarrier_init.release.cluster;" ::: "memory");
    }
    __syncwarp();
    if (lane < 9) mbar_expect(BAR(0) + 8 * lane, lane == 5 ? 65536 : ((lane == 0 || lane > 5) ? 16384 : 28672));
    __syncwarp();
    e_tma5d(sb + OFF_STG0, &mu, BAR(MB_URAW), i8 * 64, oct * 4);
    e_tma3d(sb + OFF_W, &mw, BAR(MB_FULL), hp * 32, 0, 0);
    e_tma2d(sb + OFF_X + 3 * 16384, &mx, BAR(MB_FULL), 0, rt * 256);
  } else if (warp == 13) {
    if (lane == 0) {
#pragma unroll
      for (int i = 9; i < 39; i++) mbar_init(BAR(i), i < MB_EMPTY ? 1 : (i < MB_AUX ? 4 : 5));
      asm volatile("fence.mbarrier_init.release.cluster;" ::: "memory");
    }
    __syncwarp();
    if (lane < 9) mbar_expect(BAR(MB_FULL + 8) + 8 * lane, lane < 8 ? 16384 : 131072);
  }
  const KgenRaw raw = kgen_load(P, d, tid >> 7, lane);
  const unsigned short dsk = __ldg((const unsigned short*)P.Dskip + d);
  if (warp == 12) {
#pragma unroll 1
    for (int kb = 1; kb < 4; kb++) {
      e_tma3d(sb + OFF_W + kb * 12288, &mw, BAR(MB_FULL) + 8 * kb, hp * 32, kb * 64, 0);
      e_tma2d(sb + OFF_X + (kb < 2 ? kb + 3 : kb - 2) * 16384, &mx, BAR(MB_FULL) + 8 * kb, kb * 64, rt * 256);
    }
    e_prefetch(P.x + (size_t)(rt * 256 + hp * 16) * 512, 16384);
    e_tma4d(sb + OFF_W + 4 * 12288, &mw4, BAR(MB_FULL + 4), hp * 32, 4);
    if (smem_u32(smem_raw) != SB) __trap();
    if (lane == 0) TS1(54);
  }
  const uint32_t tb = sb + OFF_T + w * T_CH;
  float k[5][4], k2048;
  {
    const uint32_t kp = wg == 3 ? sb + OFF_X + 32768 + w * 4096 : tb + (wg & 1) * 2608;
    kgen_unit(raw, lane, wg == 2 ? sb + OFF_STG0 + 16384 + w * 2048 : (kp + 127) & ~127u, blockIdx.y, k, k2048);
    TS(40 + wg);
    k2048 += __shfl_xor_sync(0xffffffffu, k2048, 16);
    k2048 += __shfl_xor_sync(0xffffffffu, k2048, 8);
    if (wg != 2 || (fu(k[0][0]) & fu(k[1][0]) & fu(k[2][0]) & fu(k[3][0]) & fu(k[4][0])) == 0xffffffffu) {
#pragma unroll
      for (int j = 0; j < 5; j++) sts128(kp + j * 512 + lane * 16, fu(k[j][0]), fu(k[j][1]), fu(k[j][2]), fu(k[j][3]));
      if (lane < 8) sts32(kp + 2560 + lane * 4, fu(k2048));
    }
  }
  __syncthreads();
  if (warp >= 12) {
    asm volatile("setmaxnreg.dec.sync.aligned.u32 32;");
    if (warp == 12) {
      nb_sync(NB_KREAD, 160);
      asm volatile("fence.proxy.async.shared::cta;" ::: "memory");
      e_tma2d(sb + OFF_X + 2 * 16384, &mx, BAR(MB_FULL + 4), 256, rt * 256);
      uint32_t slot = sb + OFF_X + 3 * 16384;
#pragma unroll 1
      for (int n = 0; n < 11; n++) {
        mbar_wait(BAR(MB_EMPTY) + 8 * n);
        const int m = n + 5;
        e_tma2d(slot, &mx, BAR(MB_FULL) + 8 * m, (m & 7) * 64, rt * 256 + (m >> 3) * 128);
        slot = slot == sb + OFF_X + 4 * 16384 ? sb + OFF_X : slot + 16384;
        if (n == 7) e_prefetch(P.wo + (size_t)b * 2048, 4096);
      }
#pragma unroll 1
      for (int i = 0; i < 8; i++) {
        mbar_wait(BAR(MB_EMPTY + 10) + 8 * ((0x54332100u >> (4 * i)) & 7));
        const int w0 = (0x54736210u >> (4 * i)) & 7;
        e_tma3d(sb + OFF_W + w0 * 16384, &mo, BAR(MB_WO), 0, w0 * 64, (hp & 3) * 2);
      }
    } else {
      if (warp == 15) {
        const uint4 v0 = __ldg((const uint4*)P.wphi + hp * 64 + lane), v1 = __ldg((const uint4*)P.wphi + hp * 64 + 32 + lane);
        sts128(sb + OFF_PHI + (lane & 1) * 256 + (lane >> 1) * 16, v0.x, v0.y, v0.z, v0.w);
        sts128(sb + OFF_PHI + 512 + (lane & 1) * 256 + (lane >> 1) * 16, v1.x, v1.y, v1.z, v1.w);
        asm volatile("fence.proxy.async.shared::cta;" ::: "memory");
        __syncwarp();
        if (lane == 0) mbar_arrive(BAR(MB_AUX));
        mbar_wait(BAR(MB_EMPTY + ZERO_STEP));
        uint4* py = P.xs + X_Y + b * 1024 + lane;
#pragma unroll 1
        for (int i = 0; i < 1024; i += 32) st_x(py + i, 0, 0, 0, 0);
        nb_arrive(NB_YZ, 160);
        nb_arrive(NB_ODONE, 320);
        if (lane == 0) TS1(55);
        return;
      }
      uint32_t* const cnt = (uint32_t*)(P.xs + X_CNT) + (warp == 13 ? i8 : 8 + rt) * 32;
      const unsigned target = (ld_x32(cnt) & ~15u) + 16;
      if (warp == 13) {
        uint4* pp = P.xs + X_PART + (hp * 8 + rt) * 144 + lane;
#pragma unroll 1
        for (int i = 0; i < 144; i += 32) if (i + lane < 144) st_x(pp + i, 0, 0, 0, 0);
      }
      nb_sync(warp == 13 ? NB_INIT : NB_ODONE, warp == 13 ? 160 : 320);
      if (lane == 0) TS1(warp == 13 ? 49 : 56);
      asm volatile("fence.proxy.async.shared::cta;" ::: "memory");
      if (lane == 0) asm volatile("red.release.gpu.global.add.u32 [%0], 1;" ::"l"(cnt) : "memory");
      if (lane == 0) TS1(warp == 13 ? 50 : 57);
      const uint32_t* pc = (warp == 13 && (lane & 1)) ? (uint32_t*)(P.xs + X_CNT) + (b >> 4) * 32 : cnt;
#pragma unroll 1
      for (int i = 0; i < SPIN_MAX; i++) {
        unsigned v;
        asm volatile("ld.acquire.gpu.global.u32 %0, [%1];" : "=r"(v) : "l"(pc) : "memory");
        if (__all_sync(0xffffffffu, (int)(v - target) >= 0)) break;
      }
      if (lane == 0) TS1(warp == 13 ? 51 : 58);
      asm volatile("fence.proxy.async.global;" ::: "memory");
      if (warp == 13) {
        mbar_wait(BAR(MB_EMPTY + 11));
        e_expect(BAR(MB_UFULL), 4 * U_CH);
        e_bulk(sb + OFF_U, P.xs + X_UT + b * (U_CH / 4), 4 * U_CH, BAR(MB_UFULL));
      } else {
        const uint4* src = P.xs + X_O + (rt * 4 + (hp >> 2)) * 4096;
        e_expect(BAR(MB_OA), 14336);
        e_bulk(sb + OFF_STG0, src + 3200, 14336, BAR(MB_OA));
        e_expect(BAR(MB_OC), 32768);
        e_bulk(sb + OFF_X + 32768, src, 32768, BAR(MB_OC));
        nb_sync(NB_BDONE, 288);
        asm volatile("fence.proxy.async.shared::cta;" ::: "memory");
        e_expect(BAR(MB_OB), 18432);
        e_bulk(sb + OFF_U, src + 2048, 18432, BAR(MB_OB));
      }
    }
    return;
  }

  asm volatile("setmaxnreg.inc.sync.aligned.u32 160;");
  const int t = tid & 127;
  const int g = lane >> 2, c = lane & 3;
  {
    if (wg == 2) {
#pragma unroll 1
      for (int q = 0; q < 3; q++) {
        const uint32_t src = q ? tb + (q - 1) * 2608 : sb + OFF_X + 32768 + w * 4096;
#pragma unroll
        for (int j = 0; j < 5; j++) {
          const uint4 v = lds128(src + j * 512 + lane * 16);
          k[j][0] += uf(v.x); k[j][1] += uf(v.y); k[j][2] += uf(v.z); k[j][3] += uf(v.w);
        }
        k2048 += uf(lds32(src + 2560 + (lane & 7) * 4));
        if (q == 0) nb_arrive(NB_KREAD, 160);
      }
#pragma unroll
      for (int o2 = 4; o2; o2 >>= 1) k2048 += __shfl_xor_sync(0xffffffffu, k2048, o2);
      if (lane == 0) k[0][0] += bf_lo(dsk);
      __syncwarp();
      TS(34);
      build_tables(tb, lane, k, k2048);
      TS(35);
      nb_sync(NB_YZ, 160);
      uint4* const g_y = P.xs + X_Y;
      conv_channel(sb + OFF_U + w * U_CH, tb, lane, g_y + (size_t)d * 256 + lane);
      nb_arrive(NB_BDONE, 288);
      TS(37);
      mbar_wait(BAR(MB_OA));
      const int lam = w * 8 + g;
      const uint4* src = g_y + (size_t)(oct * 32 + c * 8) * 256 + i8 * 32 + lam;
      uint4 v[8];
#pragma unroll 1
      for (int it = 0; it < SPIN_MAX; it++) {
        uint32_t m = 0xffffffffu;
#pragma unroll
        for (int i = 0; i < 8; i++) v[i] = ld_x(src + i * 256);
#pragma unroll
        for (int i = 0; i < 8; i++) m = min(m, v[i].x);
        if (__all_sync(0xffffffffu, m != 0)) break;
      }
      __nv_bfloat16* dst = P.out + (size_t)(i8 * 256 + (lam >> 2) * 16 + (lam & 3) * 2) * 1024 + 512 + oct * 32 + c * 8;
#pragma unroll
      for (int i = 0; i < 8; i++) *(uint4*)(dst + (size_t)((i >> 2) * 128 + ((i >> 1) & 1) * 8 + (i & 1)) * 1024) = tr_row(v, i);
      TS(38);
      GT(63);
      return;
    }
    if (wg == 1) {
      mbar_wait(BAR(MB_URAW));
      TS(48);
      uint4* dst = P.xs + X_UT + (i8 * 64 + g) * (U_CH / 16) + (c & 1) * (U_ODD / 16) + U_PAD / 16 + oct * 8 + w * 2 + (c >> 1);
      uint32_t r[8][4];
#pragma unroll
      for (int i = 0; i < 8; i++) ldsm4t(r[i], sb + OFF_STG0 + w * 4096 + lane * 128 + (((i ^ lane) & 7) << 4));
#pragma unroll
      for (int i = 0; i < 8; i++) dst[i * (U_CH / 2)] = make_uint4(r[i][0], r[i][1], r[i][2], r[i][3]);
      nb_arrive(NB_INIT, 160);
      if (lane == 0) mbar_arrive(BAR(MB_AUX));
      mbar_wait(BAR(MB_EMPTY + 6));
    }
    TS(wg * 16 + 1);
  }

  float acc[2][48];
  {
    uint32_t fb = BAR(MB_FULL) + 64 * wg;
    uint32_t da = (uint32_t)mkdesc(sb + OFF_X, 16, 0, 0) + (wg ? 1024 : 3072), db = (uint32_t)mkdesc(sb + OFF_W, 4096, 0, 0);
    constexpr uint64_t ha = mkdesc(0, 0, 1024, 1), hb = mkdesc(0, 0, 512, 2);
#pragma unroll 1
    for (int kb = 0; kb < 8; kb++) {
      mbar_wait(fb);
      if (kb == 0) TS(wg * 16 + 2);
      WG_FENCE();
#pragma unroll
      for (int k = 0; k < 4; k++) {
        wgmma_ss_n96(acc[0], ha | (da + 2 * k), hb | (db + 64 * k), k ? 1 : kb);
        wgmma_ss_n96(acc[1], ha | (da + 2 * k + 512), hb | (db + 64 * k), k ? 1 : kb);
      }
      WG_COMMIT();
      WG_WAIT(1);
      if (kb > 0 && lane == 0) mbar_arrive(fb + 8 * (MB_EMPTY - MB_FULL - 1));
      fb += 8; db += 768;
      da = da == (uint32_t)mkdesc(sb + OFF_X + 65536, 16, 0, 0) ? da - 4096 : da + 1024;
    }
    WG_WAIT(0);
    if (lane == 0) mbar_arrive(fb + 8 * (MB_EMPTY - MB_FULL - 1));
    mbar_wait(fb + 8 * (MB_EMPTY - MB_FULL - 1));
  }
  TS(wg * 16 + 3);

  constexpr uint32_t stg0 = sb + OFF_STG0, stg1 = sb + OFF_X + 32768;
  const uint32_t sl = (wg ? stg1 : stg0) + w * 3072 + lane * 16;
  uint32_t pw[32], eq[32];
  {
    uint4 af[8];
#pragma unroll
    for (int u = 0; u < 8; u++) {
      const float* a = acc[(u >> 1) & 1] + (u < 4 ? 16 : 0) + 8 * (u & 1);
      af[u] = make_uint4(pack_bf(a[0], a[1]), pack_bf(a[2], a[3]), pack_bf(a[4], a[5]), pack_bf(a[6], a[7]));
    }
    mbar_wait(BAR(MB_AUX));
    float p[8][8];
    WG_FENCE();
#pragma unroll
    for (int u = 0; u < 8; u++) wgmma_rs_n16(p[u], af[u], mkdesc(sb + OFF_PHI + (u & 1) * 512, 128, 256, 0), 0);
    WG_COMMIT();
#pragma unroll
    for (int i = 0; i < 4; i++) {
      const float* a = acc[i >> 1] + 32 + 8 * (i & 1);
      stsm4(sl + (i >> 1) * 12288 + 2048 + (i & 1) * 512, pack_bf(a[0], a[1]), pack_bf(a[2], a[3]), pack_bf(a[4], a[5]), pack_bf(a[6], a[7]));
    }
    WG_WAIT(0);
#pragma unroll
    for (int u = 0; u < 8; u++) {
      pw[4 * u] = pack_bf(p[u][0], p[u][2]); pw[4 * u + 1] = pack_bf(p[u][1], p[u][3]);
      pw[4 * u + 2] = pack_bf(p[u][4], p[u][6]); pw[4 * u + 3] = pack_bf(p[u][5], p[u][7]);
    }
  }
  uint32_t ek[32];
  if (wg == 0) {
#pragma unroll
    for (int i = 0; i < 16; i++) { const uint32_t x = pw[i]; pw[i] = pw[16 + i]; pw[16 + i] = x; }
  }
#pragma unroll 1
  for (int it = 0; it < 2; it++) {
#pragma unroll
    for (int i = 0; i < 32; i++) ek[i] = eq[i];
#pragma unroll
    for (int u = 0; u < 4; u++) dual_exp(pw + 4 * u, eq + 8 * u);
    if (it != wg) {
      TS(wg * 16 + 12);
      mbar_wait(BAR(MB_EMPTY + 15));
#pragma unroll
      for (int i = 0; i < 8; i++) norm_store(eq + 4 * i, sl + (i >> 2) * 12288 + (i & 3) * 512);
      if (wg) nb_arrive(NB_ST0, 256);
    }
#pragma unroll
    for (int i = 0; i < 16; i++) pw[i] = pw[i + 16];
  }
  TS(wg * 16 + 4);
  uint4* const g_part = P.xs + X_PART;
  uint4* const g_o = P.xs + X_O;
  const uint32_t kvs = stg0;
  if (wg == 0) {
#pragma unroll
    for (int i = 0; i < 32; i++) eq[i] = ek[i];
    nb_sync(NB_WG0, 128);
    mbar_wait(BAR(MB_UFULL));
    float kv[12], kw[12];
#pragma unroll
    for (int i = 0; i < 12; i++) kv[i] = kw[i] = 0.f;
    const int mi = lane >> 3;
    const uint32_t ao = w * 512 + (lane & 7) * 16 + ((mi & 1) * 2 + (mi >> 1)) * 128, bo = 2048 + (w >> 1) * 512 + lane * 16;
#pragma unroll 1
    for (int j = 0; j < 2; j++) {
      if (j) nb_sync(NB_ST0, 256);
      const uint32_t sg = j ? stg1 : stg0;
      uint32_t a[8][4], bb[8][4];
#pragma unroll
      for (int s = 0; s < 8; s++) { ldsm4t(a[s], sg + s * 3072 + ao); ldsm4t(bb[s], sg + s * 3072 + bo); }
#pragma unroll
      for (int s = 0; s < 8; s++) {
        float* o = (s & 1) ? kw : kv;
        mma(o[0], o[1], o[2], o[3], a[s][0], a[s][1], a[s][2], a[s][3], bb[s][0], bb[s][1]);
        mma(o[4], o[5], o[6], o[7], a[s][0], a[s][1], a[s][2], a[s][3], bb[s][2], bb[s][3]);
        mma(o[8], o[9], o[10], o[11], a[s][0], a[s][1], a[s][2], a[s][3], 0x3F803F80u, 0x3F803F80u);
      }
    }
#pragma unroll
    for (int i = 0; i < 12; i++) kv[i] += kw[i];
    uint4* pp = g_part + (size_t)(hp * 8 + rt) * 144;
    st_x(pp + t, nz(pack_bf(kv[0], kv[1])), pack_bf(kv[2], kv[3]), pack_bf(kv[4], kv[5]), pack_bf(kv[6], kv[7]));
    if (c < 2) st_x32((uint32_t*)(pp + 128) + w * 16 + c * 8 + g, nz(fu(c ? kv[10] : kv[8])));
    TS(5);
    const uint4* ps = g_part + (size_t)hp * 8 * 144 + t;
    const uint32_t* zs = (const uint32_t*)(g_part + (size_t)(hp * 8 + (lane >> 4) * 4) * 144 + 128) + w * 16 + (lane & 15);
    uint4 v[8];
    uint32_t zv[4];
#pragma unroll 1
    for (int it = 0; it < SPIN_MAX; it++) {
#pragma unroll
      for (int i = 0; i < 8; i++) v[i] = ld_x(ps + i * 144);
#pragma unroll
      for (int i = 0; i < 4; i++) zv[i] = ld_x32(zs + i * 576);
      uint32_t m = min(min(zv[0], zv[1]), min(zv[2], zv[3]));
#pragma unroll
      for (int i = 0; i < 8; i++) m = min(m, v[i].x);
      if (__all_sync(0xffffffffu, m != 0)) break;
    }
    float s4[4][4];
#pragma unroll
    for (int i = 0; i < 4; i++) s4[i][0] = s4[i][1] = s4[i][2] = s4[i][3] = 0.f;
    const uint32_t eye = (g >> 1) == c ? ((g & 1) ? 0x3F800000u : 0x3F80u) : 0u;
#pragma unroll
    for (int r = 0; r < 8; r++) {
      mma_k8(s4[(r & 1) * 2], v[r].x, v[r].y, eye);
      mma_k8(s4[(r & 1) * 2 + 1], v[r].z, v[r].w, eye);
    }
    float s[8];
#pragma unroll
    for (int i = 0; i < 8; i++) s[i] = s4[i >> 2][i & 3] + s4[2 + (i >> 2)][i & 3];
    float zsum = (uf(zv[0]) + uf(zv[1])) + (uf(zv[2]) + uf(zv[3]));
    zsum += __shfl_xor_sync(0xffffffffu, zsum, 16);
    stsm4(kvs + w * 512 + lane * 16, pack_bf(s[0], s[1]), pack_bf(s[2], s[3]), pack_bf(s[4], s[5]), pack_bf(s[6], s[7]));
    sts16(kvs + 2048 + (lane >> 4) * 128 + (w * 16 + (lane & 15)) * 2, lane < 16 ? pack_bf(zsum, 0.f) : 0x3F80u);
    TS(6);
  }
  nb_sync(NB_KV, 256);
  {
    uint32_t kb_[4][4], zb[8];
#pragma unroll
    for (int i = 0; i < 4; i++) ldsm4t(kb_[i], kvs + i * 512 + lane * 16);
#pragma unroll
    for (int i = 0; i < 8; i++) zb[i] = lds32(kvs + 2048 + (g & 1) * 128 + i * 16 + c * 4);
    uint32_t* od = (uint32_t*)(g_o + (size_t)((rt * 4 + wg * 2) * 32 + hp * 2) * 128) + w * 64 + lane;
#pragma unroll
    for (int mt = 0; mt < 2; mt++) {
#pragma unroll
      for (int h = 0; h < 2; h++) {
        const uint32_t* e = eq + 16 * mt + 8 * h;
        float n[8], nm[8], dp[4], dm[4];
        mma0(dp[0], dp[1], dp[2], dp[3], e[0], e[1], e[2], e[3], zb[4 * h], zb[4 * h + 1]);
        mma0(dm[0], dm[1], dm[2], dm[3], e[4], e[5], e[6], e[7], zb[4 * h + 2], zb[4 * h + 3]);
        mma0(n[0], n[1], n[2], n[3], e[0], e[1], e[2], e[3], kb_[2 * h][0], kb_[2 * h][1]);
        mma0(nm[0], nm[1], nm[2], nm[3], e[4], e[5], e[6], e[7], kb_[2 * h + 1][0], kb_[2 * h + 1][1]);
        mma0(n[4], n[5], n[6], n[7], e[0], e[1], e[2], e[3], kb_[2 * h][2], kb_[2 * h][3]);
        mma0(nm[4], nm[5], nm[6], nm[7], e[4], e[5], e[6], e[7], kb_[2 * h + 1][2], kb_[2 * h + 1][3]);
        const float q0 = dp[1] * rcp(dm[1]), q1 = dp[3] * rcp(dm[3]);
        const float r0 = rcp(fmaf(dm[0], q0, fmaf(dp[1], 1e-6f, dp[0]))), r1 = rcp(fmaf(dm[2], q1, fmaf(dp[3], 1e-6f, dp[2])));
#pragma unroll
        for (int i = 0; i < 8; i++) n[i] = fmaf(nm[i], (i & 2) ? q1 : q0, n[i]);
        od[h * 512] = pack_bf(n[0] * r0, n[1] * r0);
        od[h * 512 + 32] = pack_bf(n[2] * r1, n[3] * r1);
        od[h * 512 + 256] = pack_bf(n[4] * r0, n[5] * r0);
        od[h * 512 + 288] = pack_bf(n[6] * r1, n[7] * r1);
      }
      od += 16384;
    }
  }
  TS(wg * 16 + 7);
  nb_arrive(NB_ODONE, 320);
  if (wg) return;
  mbar_wait(BAR(MB_WO));
  mbar_wait(BAR(MB_OA));
  TS(8);
  nb_sync(NB_BDONE, 288);
  TS(9);
  float oc[64];
  {
    constexpr uint64_t ha = mkdesc(0, 0, 128, 0), hb = mkdesc(0, 0, 1024, 1);
    constexpr uint32_t da0 = (uint32_t)mkdesc(stg1, 1024, 0, 0), db0 = (uint32_t)mkdesc(sb + OFF_W, 8192, 0, 0);
#pragma unroll 1
    for (int j = 0; j < 8; j++) {
      const int kb = (j + 7) & 7;
      if ((j & 3) == 1) mbar_wait(j == 1 ? BAR(MB_OC) : BAR(MB_OB));
      WG_FENCE();
#pragma unroll
      for (int k = 0; k < 4; k++) wgmma_ss_n128(oc, ha | (da0 + 512 * kb + 128 * k), hb | (db0 + 1024 * kb + 128 * k), k ? 1 : j);
      WG_COMMIT();
    }
    WG_WAIT(0);
  }
  TS(10);
  nb_sync(NB_WG0, 128);
  const uint32_t ot = sb + OFF_W + w * 4096;
#pragma unroll
  for (int i = 0; i < 16; i += 2)
    stsm4(ot + (i >> 3) * 2048 + (lane & 15) * 128 + (((i + (lane >> 4)) ^ lane) & 7) * 16, pack_bf(oc[4 * i], oc[4 * i + 1]),
          pack_bf(oc[4 * i + 2], oc[4 * i + 3]), pack_bf(oc[4 * i + 4], oc[4 * i + 5]), pack_bf(oc[4 * i + 6], oc[4 * i + 7]));
  asm volatile("fence.proxy.async.shared::cta;" ::: "memory");
  __syncwarp();
  e_store3d(&mout, ot, (rt * 4 + (hp >> 2)) * 64 + w * 16, (hp & 3) * 2);
  TS(wg * 16 + 11);
  GT(61 + wg);
}

typedef CUresult (*EncodeFn)(CUtensorMap*, CUtensorMapDataType, cuuint32_t, void*, const cuuint64_t*, const cuuint64_t*,
                             const cuuint32_t*, const cuuint32_t*, CUtensorMapInterleave, CUtensorMapSwizzle,
                             CUtensorMapL2promotion, CUtensorMapFloatOOBfill);

}

extern "C" void kernel_launch(void* const* d_in, const int* in_sizes, int n_in, void* d_out, int out_size) {
  (void)in_sizes; (void)n_in; (void)out_size;
  void* fn = nullptr;
  cudaDriverEntryPointQueryResult qr;
  cudaGetDriverEntryPoint("cuTensorMapEncodeTiled", &fn, cudaEnableDefault, &qr);
  EncodeFn enc = (EncodeFn)fn;
  CUtensorMap mx, mw, mo, mu, mout, mw4;
  const cuuint32_t es[5] = {1, 1, 1, 1, 1};
  {
    cuuint64_t dims[2] = {512, 2048}, st[1] = {1024};
    cuuint32_t box[2] = {64, 128};
    enc(&mx, CU_TENSOR_MAP_DATA_TYPE_BFLOAT16, 2, d_in[0], dims, st, box, es, CU_TENSOR_MAP_INTERLEAVE_NONE,
        CU_TENSOR_MAP_SWIZZLE_128B, CU_TENSOR_MAP_L2_PROMOTION_L2_128B, CU_TENSOR_MAP_FLOAT_OOB_FILL_NONE);
  }
  {
    cuuint64_t dims[3] = {512, 512, 3}, st[2] = {3072, 1024};
    cuuint32_t box[3] = {32, 64, 3};
    enc(&mw, CU_TENSOR_MAP_DATA_TYPE_BFLOAT16, 3, d_in[1], dims, st, box, es, CU_TENSOR_MAP_INTERLEAVE_NONE,
        CU_TENSOR_MAP_SWIZZLE_64B, CU_TENSOR_MAP_L2_PROMOTION_L2_128B, CU_TENSOR_MAP_FLOAT_OOB_FILL_NONE);
  }
  {
    cuuint64_t dims[3] = {64, 512, 8}, st[2] = {1024, 128};
    cuuint32_t box[3] = {64, 64, 2};
    enc(&mo, CU_TENSOR_MAP_DATA_TYPE_BFLOAT16, 3, d_in[3], dims, st, box, es, CU_TENSOR_MAP_INTERLEAVE_NONE,
        CU_TENSOR_MAP_SWIZZLE_128B, CU_TENSOR_MAP_L2_PROMOTION_L2_128B, CU_TENSOR_MAP_FLOAT_OOB_FILL_NONE);
  }
  {
    cuuint64_t dims[5] = {512, 2, 4, 4, 64}, st[4] = {1024, 8192, 2048, 32768};
    cuuint32_t box[5] = {64, 2, 4, 4, 4};
    enc(&mu, CU_TENSOR_MAP_DATA_TYPE_BFLOAT16, 5, d_in[4], dims, st, box, es, CU_TENSOR_MAP_INTERLEAVE_NONE,
        CU_TENSOR_MAP_SWIZZLE_128B, CU_TENSOR_MAP_L2_PROMOTION_L2_128B, CU_TENSOR_MAP_FLOAT_OOB_FILL_NONE);
  }
  {
    cuuint64_t dims[3] = {64, 2048, 16}, st[2] = {2048, 128};
    cuuint32_t box[3] = {64, 16, 2};
    enc(&mout, CU_TENSOR_MAP_DATA_TYPE_BFLOAT16, 3, d_out, dims, st, box, es, CU_TENSOR_MAP_INTERLEAVE_NONE,
        CU_TENSOR_MAP_SWIZZLE_128B, CU_TENSOR_MAP_L2_PROMOTION_NONE, CU_TENSOR_MAP_FLOAT_OOB_FILL_NONE);
  }
  {
    cuuint64_t dims[4] = {512, 64, 3, 8}, st[3] = {3072, 1024, 64 * 3072};
    cuuint32_t box[4] = {32, 64, 3, 4};
    enc(&mw4, CU_TENSOR_MAP_DATA_TYPE_BFLOAT16, 4, d_in[1], dims, st, box, es, CU_TENSOR_MAP_INTERLEAVE_NONE,
        CU_TENSOR_MAP_SWIZZLE_64B, CU_TENSOR_MAP_L2_PROMOTION_L2_128B, CU_TENSOR_MAP_FLOAT_OOB_FILL_NONE);
  }
  Params P;
  P.x = (const __nv_bfloat16*)d_in[0];
  P.wphi = (const __nv_bfloat16*)d_in[2];
  P.wo = (const __nv_bfloat16*)d_in[3];
  P.logA = (const __nv_bfloat16*)d_in[5];
  P.Aim = (const __nv_bfloat16*)d_in[6];
  P.Cre = (const __nv_bfloat16*)d_in[7];
  P.Cim = (const __nv_bfloat16*)d_in[8];
  P.logdt = (const __nv_bfloat16*)d_in[9];
  P.Dskip = (const __nv_bfloat16*)d_in[10];
  P.out = (__nv_bfloat16*)d_out;
  cudaGetSymbolAddress((void**)&P.xs, g_x);
  P.ts = nullptr;
  cudaFuncSetAttribute(fused_kernel, cudaFuncAttributeMaxDynamicSharedMemorySize, SMEM_BYTES);
  fused_kernel<<<NCTA, NTHREADS, SMEM_BYTES>>>(P, mx, mw, mo, mu, mout, mw4);
}
```

```cpp
#include <cuda_runtime.h>
#include <cuda_bf16.h>
#include <cuda_fp16.h>
#include <cuda.h>
#include <stdint.h>

#define DBG_TS 0

namespace {

constexpr int NTHREADS = 512;
constexpr int NCTA = 128;
constexpr int OFF_W = 0;
constexpr int OFF_X = 98304;
constexpr int OFF_U = OFF_X + 65536;
constexpr int U_CH = 4416, U_ODD = 2240, U_PAD = 128;
constexpr int OFF_STG0 = OFF_U + 18432;
constexpr int OFF_T = OFF_STG0 + 24576;
constexpr int T_CH = 5216;
constexpr int T_D = 0;
constexpr int T_5 = 2144;
constexpr int T_3 = T_5 + 384;
constexpr int T_7 = T_5 + 1024;
constexpr int T_9 = T_7 + 320;
constexpr int T_KC = T_9 + 320;
constexpr int T_ST = T_5 - 1024;
constexpr int OFF_PHI = OFF_T + 4 * T_CH;
constexpr int OFF_BAR = OFF_PHI + 1024;
constexpr int SMEM_BYTES = OFF_BAR + 512 + 256 * DBG_TS;
constexpr uint32_t SB = 1024;
static_assert(T_KC + 2 * 656 <= T_CH, "table size");
static_assert(SMEM_BYTES <= 232448, "smem");
constexpr int MB_URAW = 0, MB_FULL = 1  , MB_WO = 17, MB_UFULL = 18, MB_OA = 19, MB_OB = 20, MB_OC = 21,
              MB_EMPTY = 22  , MB_AUX = 38;
__host__ __device__ constexpr uint32_t BAR(int i) { return SB + OFF_BAR + 8 * i; }
constexpr int NB_WG0 = 1, NB_ODONE = 2, NB_ST0 = 3  , NB_KV = 5, NB_YZ = 6, NB_INIT = 7, NB_PREP = 8, NB_PROD = 9, NB_KREAD = 10, NB_BDONE = 11, NB_ZERO = 12;
#define U_AT 2
#define ZERO_STEP 7
constexpr int SPIN_MAX = 1 << 16;

constexpr int X_CNT = 0;
constexpr int X_PART = 128;
constexpr int X_O = X_PART + 16 * 8 * 144;
constexpr int X_Y = X_O + 32 * 32 * 128;
constexpr int X_UT = X_Y + 512 * 8 * 32;
constexpr int X_SIZE = X_UT + 512 * (U_CH / 16);
__device__ __align__(128) uint4 g_x[X_SIZE];
extern __shared__ uint8_t smem_raw[];
#define TS(i) do {} while (0)
#define TS1(i) do {} while (0)
#define GT(i) do {} while (0)
#define TSDUMP(base) do {} while (0)

__device__ __forceinline__ uint32_t smem_u32(const void* p) { return (uint32_t)__cvta_generic_to_shared(p); }
__device__ __forceinline__ void mbar_arrive(uint32_t b) {
  asm volatile("mbarrier.arrive.shared::cta.b64 _, [%0];" ::"r"(b) : "memory");
}
__device__ __forceinline__ void mbar_wait(uint32_t b) {
  uint32_t done = 0;
#pragma unroll 1
  for (int i = 0; i < SPIN_MAX && !done; i++) {
    asm volatile("{\n.reg .pred p;\nmbarrier.try_wait.parity.shared::cta.b64 p, [%1], 0, 4000;\nselp.u32 %0, 1, 0, p;\n}\n"
                 : "=r"(done) : "r"(b) : "memory");
  }
}
__device__ __forceinline__ void mbar_spin(uint32_t b) {
  uint32_t done = 0;
#pragma unroll 1
  for (int i = 0; i < (SPIN_MAX << 4) && !done; i++) {
    asm volatile("{\n.reg .pred p;\nmbarrier.try_wait.parity.shared::cta.b64 p, [%1], 0;\nselp.u32 %0, 1, 0, p;\n}\n"
                 : "=r"(done) : "r"(b) : "memory");
  }
}
__device__ __forceinline__ void mbar_init(uint32_t b, int n) {
  asm volatile("mbarrier.init.shared::cta.b64 [%0], %1;" ::"r"(b), "r"(n) : "memory");
}
__device__ __forceinline__ void mbar_expect(uint32_t b, int bytes) {
  asm volatile("mbarrier.arrive.expect_tx.shared::cta.b64 _, [%0], %1;" ::"r"(b), "r"(bytes) : "memory");
}
__device__ __forceinline__ void nb_sync(int id, int n) { asm volatile("bar.sync %0, %1;" ::"r"(id), "r"(n) : "memory"); }
__device__ __forceinline__ void nb_arrive(int id, int n) { asm volatile("bar.arrive %0, %1;" ::"r"(id), "r"(n) : "memory"); }
#define ELECT "{\n.reg .pred p;\nelect.sync _|p, 0xffffffff;\n@p "
__device__ __forceinline__ void e_expect(uint32_t b, int bytes) {
  asm volatile(ELECT "mbarrier.arrive.expect_tx.shared::cta.b64 _, [%0], %1;\n}\n" ::"r"(b), "r"(bytes) : "memory");
}
__device__ __forceinline__ void e_tma2d(uint32_t dst, const CUtensorMap* m, uint32_t bar, int c0, int c1) {
  asm volatile(ELECT "cp.async.bulk.tensor.2d.shared::cluster.global.mbarrier::complete_tx::bytes [%0], [%1, {%3,%4}], [%2];\n}\n"
               ::"r"(dst), "l"(m), "r"(bar), "r"(c0), "r"(c1) : "memory");
}
__device__ __forceinline__ void e_tma3d(uint32_t dst, const CUtensorMap* m, uint32_t bar, int c0, int c1, int c2) {
  asm volatile(ELECT "cp.async.bulk.tensor.3d.shared::cluster.global.mbarrier::complete_tx::bytes [%0], [%1, {%3,%4,%5}], [%2];\n}\n"
               ::"r"(dst), "l"(m), "r"(bar), "r"(c0), "r"(c1), "r"(c2) : "memory");
}
__device__ __forceinline__ void e_tma4d(uint32_t dst, const CUtensorMap* m, uint32_t bar, int c0, int c3) {
  asm volatile(ELECT "cp.async.bulk.tensor.4d.shared::cluster.global.mbarrier::complete_tx::bytes [%0], [%1, {%3,%5,%5,%4}], [%2];\n}\n"
               ::"r"(dst), "l"(m), "r"(bar), "r"(c0), "r"(c3), "r"(0) : "memory");
}
__device__ __forceinline__ void e_tma5d(uint32_t dst, const CUtensorMap* m, uint32_t bar, int c0, int c4) {
  asm volatile(ELECT "cp.async.bulk.tensor.5d.shared::cluster.global.mbarrier::complete_tx::bytes [%0], [%1, {%3,%5,%5,%5,%4}], [%2];\n}\n"
               ::"r"(dst), "l"(m), "r"(bar), "r"(c0), "r"(c4), "r"(0) : "memory");
}
__device__ __forceinline__ void e_bulk(uint32_t dst, const void* src, int bytes, uint32_t bar) {
  asm volatile(ELECT "cp.async.bulk.shared::cluster.global.mbarrier::complete_tx::bytes [%0], [%1], %2, [%3];\n}\n"
               ::"r"(dst), "l"(src), "r"(bytes), "r"(bar) : "memory");
}
__device__ __forceinline__ void e_prefetch(const void* p, int bytes) {
  asm volatile(ELECT "cp.async.bulk.prefetch.L2.global [%0], %1;\n}\n" ::"l"(p), "r"(bytes) : "memory");
}
__device__ __forceinline__ void e_store3d(const CUtensorMap* m, uint32_t src, int c1, int c2) {
  asm volatile(ELECT "cp.async.bulk.tensor.3d.global.shared::cta.bulk_group [%0, {%4,%2,%3}], [%1];\n"
               "@p cp.async.bulk.commit_group;\n@p cp.async.bulk.wait_group.read 0;\n}\n"
               ::"l"(m), "r"(src), "r"(c1), "r"(c2), "r"(0) : "memory");
}
__host__ __device__ constexpr uint64_t mkdesc(uint32_t addr, uint32_t lbo, uint32_t sbo, int swz) {
  return (uint64_t)((addr & 0x3FFFF) >> 4) | ((uint64_t)(lbo >> 4) << 16) | ((uint64_t)(sbo >> 4) << 32) |
         ((uint64_t)swz << 62);
}
#define WG_FENCE() asm volatile("wgmma.fence.sync.aligned;" ::: "memory")
#define WG_COMMIT() asm volatile("wgmma.commit_group.sync.aligned;" ::: "memory")
#define WG_WAIT(n) asm volatile("wgmma.wait_group.sync.aligned " #n ";" ::: "memory")

__device__ __forceinline__ void mma(float& d0, float& d1, float& d2, float& d3, uint32_t a0, uint32_t a1, uint32_t a2,
                                    uint32_t a3, uint32_t b0, uint32_t b1) {
  asm volatile("mma.sync.aligned.m16n8k16.row.col.f32.bf16.bf16.f32 {%0,%1,%2,%3},{%4,%5,%6,%7},{%8,%9},{%0,%1,%2,%3};"
               : "+f"(d0), "+f"(d1), "+f"(d2), "+f"(d3)
               : "r"(a0), "r"(a1), "r"(a2), "r"(a3), "r"(b0), "r"(b1));
}
__device__ __forceinline__ void mmac(float (&d)[4], uint32_t a0, uint32_t a1, uint32_t a2, uint32_t a3, uint32_t b0,
                                     uint32_t b1, const float (&c)[4]) {
  asm volatile("mma.sync.aligned.m16n8k16.row.col.f32.bf16.bf16.f32 {%0,%1,%2,%3},{%4,%5,%6,%7},{%8,%9},{%10,%11,%12,%13};"
               : "=f"(d[0]), "=f"(d[1]), "=f"(d[2]), "=f"(d[3])
               : "r"(a0), "r"(a1), "r"(a2), "r"(a3), "r"(b0), "r"(b1), "f"(c[0]), "f"(c[1]), "f"(c[2]), "f"(c[3]));
}
__device__ __forceinline__ void mma_p(int p, float (&d)[4], uint32_t a0, uint32_t a1, uint32_t a2, uint32_t a3, uint32_t b0, uint32_t b1) {
  asm volatile("{\n.reg .pred q;\nsetp.ne.b32 q, %10, 0;\n"
               "@q mma.sync.aligned.m16n8k16.row.col.f32.bf16.bf16.f32 {%0,%1,%2,%3},{%4,%5,%6,%7},{%8,%9},{%0,%1,%2,%3};\n}\n"
               : "+f"(d[0]), "+f"(d[1]), "+f"(d[2]), "+f"(d[3])
               : "r"(a0), "r"(a1), "r"(a2), "r"(a3), "r"(b0), "r"(b1), "r"(p));
}
__device__ __forceinline__ void mmac_p(int p, float (&d)[4], uint32_t a0, uint32_t a1, uint32_t a2, uint32_t a3, uint32_t b0,
                                       uint32_t b1, const float (&c)[4]) {
  asm volatile("{\n.reg .pred q;\nsetp.ne.b32 q, %14, 0;\n"
               "@q mma.sync.aligned.m16n8k16.row.col.f32.bf16.bf16.f32 {%0,%1,%2,%3},{%4,%5,%6,%7},{%8,%9},{%10,%11,%12,%13};\n}\n"
               : "+f"(d[0]), "+f"(d[1]), "+f"(d[2]), "+f"(d[3])
               : "r"(a0), "r"(a1), "r"(a2), "r"(a3), "r"(b0), "r"(b1), "f"(c[0]), "f"(c[1]), "f"(c[2]), "f"(c[3]), "r"(p));
}
__device__ __forceinline__ void mma_h(float (&d)[4], const uint32_t (&a)[4], uint32_t b0, uint32_t b1) {
  asm volatile("mma.sync.aligned.m16n8k16.row.col.f32.f16.f16.f32 {%0,%1,%2,%3},{%4,%5,%6,%7},{%8,%9},{%0,%1,%2,%3};"
               : "+f"(d[0]), "+f"(d[1]), "+f"(d[2]), "+f"(d[3]) : "r"(a[0]), "r"(a[1]), "r"(a[2]), "r"(a[3]), "r"(b0), "r"(b1));
}
__device__ __forceinline__ void mma_k8(float (&d)[4], uint32_t a0, uint32_t a1, uint32_t b0) {
  asm volatile("mma.sync.aligned.m16n8k8.row.col.f32.bf16.bf16.f32 {%0,%1,%2,%3},{%4,%5},{%6},{%0,%1,%2,%3};"
               : "+f"(d[0]), "+f"(d[1]), "+f"(d[2]), "+f"(d[3]) : "r"(a0), "r"(a1), "r"(b0));
}
__device__ __forceinline__ void mma0(float& d0, float& d1, float& d2, float& d3, uint32_t a0, uint32_t a1, uint32_t a2,
                                     uint32_t a3, uint32_t b0, uint32_t b1) {
  asm volatile("mma.sync.aligned.m16n8k16.row.col.f32.bf16.bf16.f32 {%0,%1,%2,%3},{%4,%5,%6,%7},{%8,%9},{%10,%10,%10,%10};"
               : "=f"(d0), "=f"(d1), "=f"(d2), "=f"(d3)
               : "r"(a0), "r"(a1), "r"(a2), "r"(a3), "r"(b0), "r"(b1), "f"(0.f));
}
__device__ __forceinline__ uint32_t pack_bf(float lo, float hi) {
  uint32_t r;
  asm("cvt.rn.bf16x2.f32 %0, %1, %2;" : "=r"(r) : "f"(hi), "f"(lo));
  return r;
}
__device__ __forceinline__ float bf_lo(uint32_t w) { return __uint_as_float(w << 16); }
__device__ __forceinline__ float bf_hi(uint32_t w) { return __uint_as_float(w & 0xffff0000u); }
__device__ __forceinline__ float bf_round(float x) { return __bfloat162float(__float2bfloat16_rn(x)); }
__device__ __forceinline__ uint32_t bmax2(uint32_t a, uint32_t b) {
  uint32_t r; asm("max.bf16x2 %0, %1, %2;" : "=r"(r) : "r"(a), "r"(b)); return r;
}
__device__ __forceinline__ uint32_t bmin2(uint32_t a, uint32_t b) {
  uint32_t r; asm("min.bf16x2 %0, %1, %2;" : "=r"(r) : "r"(a), "r"(b)); return r;
}
__device__ __forceinline__ float ex2(float x) { float r; asm("ex2.approx.ftz.f32 %0, %1;" : "=f"(r) : "f"(x)); return r; }
__device__ __forceinline__ float rcp(float x) { float r; asm("rcp.approx.ftz.f32 %0, %1;" : "=f"(r) : "f"(x)); return r; }
__device__ __forceinline__ void ldsm4(uint32_t (&r)[4], uint32_t a) {
  asm volatile("ldmatrix.sync.aligned.m8n8.x4.shared.b16 {%0,%1,%2,%3}, [%4];"
               : "=r"(r[0]), "=r"(r[1]), "=r"(r[2]), "=r"(r[3]) : "r"(a) : "memory");
}
__device__ __forceinline__ void ldsm4t(uint32_t (&r)[4], uint32_t a) {
  asm volatile("ldmatrix.sync.aligned.m8n8.x4.trans.shared.b16 {%0,%1,%2,%3}, [%4];"
               : "=r"(r[0]), "=r"(r[1]), "=r"(r[2]), "=r"(r[3]) : "r"(a) : "memory");
}
__device__ __forceinline__ void stsm4(uint32_t a, uint32_t r0, uint32_t r1, uint32_t r2, uint32_t r3) {
  asm volatile("stmatrix.sync.aligned.m8n8.x4.shared.b16 [%0], {%1,%2,%3,%4};"
               ::"r"(a), "r"(r0), "r"(r1), "r"(r2), "r"(r3) : "memory");
}
__device__ __forceinline__ uint32_t lds32(uint32_t a) {
  uint32_t r; asm volatile("ld.shared.u32 %0, [%1];" : "=r"(r) : "r"(a) : "memory"); return r;
}
__device__ __forceinline__ uint32_t lds16(uint32_t a) {
  uint32_t r; asm volatile("{\n.reg .u16 h;\nld.shared.u16 h, [%1];\ncvt.u32.u16 %0, h;\n}\n" : "=r"(r) : "r"(a) : "memory"); return r;
}
__device__ __forceinline__ uint2 lds64(uint32_t a) {
  uint2 r; asm volatile("ld.shared.v2.u32 {%0,%1}, [%2];" : "=r"(r.x), "=r"(r.y) : "r"(a) : "memory"); return r;
}
__device__ __forceinline__ uint4 lds128(uint32_t a) {
  uint4 r;
  asm volatile("ld.shared.v4.u32 {%0,%1,%2,%3}, [%4];" : "=r"(r.x), "=r"(r.y), "=r"(r.z), "=r"(r.w) : "r"(a) : "memory");
  return r;
}
__device__ __forceinline__ void sts32(uint32_t a, uint32_t v) { asm volatile("st.shared.u32 [%0], %1;" ::"r"(a), "r"(v) : "memory"); }
__device__ __forceinline__ void sts16(uint32_t a, uint32_t v) {
  asm volatile("{\n.reg .u16 h;\ncvt.u16.u32 h, %1;\nst.shared.u16 [%0], h;\n}\n" ::"r"(a), "r"(v) : "memory");
}
__device__ __forceinline__ void sts64(uint32_t a, uint32_t x, uint32_t y) {
  asm volatile("st.shared.v2.u32 [%0], {%1,%2};" ::"r"(a), "r"(x), "r"(y) : "memory");
}
__device__ __forceinline__ void sts128(uint32_t a, uint32_t x, uint32_t y, uint32_t z, uint32_t w) {
  asm volatile("st.shared.v4.u32 [%0], {%1,%2,%3,%4};" ::"r"(a), "r"(x), "r"(y), "r"(z), "r"(w) : "memory");
}
__device__ __forceinline__ uint4 ld_x(const uint4* p) {
  uint4 r;
  asm volatile("{\n.reg .b128 t;\nld.relaxed.gpu.global.b128 t, [%4];\nmov.b128 {%0,%1,%2,%3}, t;\n}\n"
               : "=r"(r.x), "=r"(r.y), "=r"(r.z), "=r"(r.w) : "l"(p) : "memory");
  return r;
}
__device__ __forceinline__ uint32_t ld_x32(const uint32_t* p) {
  uint32_t r; asm volatile("ld.relaxed.gpu.global.u32 %0, [%1];" : "=r"(r) : "l"(p) : "memory"); return r;
}
__device__ __forceinline__ void st_x(uint4* p, uint32_t x, uint32_t y, uint32_t z, uint32_t w) {
  asm volatile("{\n.reg .b128 t;\nmov.b128 t, {%1,%2,%3,%4};\nst.relaxed.gpu.global.b128 [%0], t;\n}\n"
               ::"l"(p), "r"(x), "r"(y), "r"(z), "r"(w) : "memory");
}
__device__ __forceinline__ void st_x_p(int p, uint4* a, uint32_t x, uint32_t y, uint32_t z, uint32_t w) {
  asm volatile("{\n.reg .b128 t;\n.reg .pred q;\nsetp.ne.b32 q, %5, 0;\nmov.b128 t, {%1,%2,%3,%4};\n@q st.relaxed.gpu.global.b128 [%0], t;\n}\n"
               ::"l"(a), "r"(x), "r"(y), "r"(z), "r"(w), "r"(p) : "memory");
}
__device__ __forceinline__ void sts64_p(int p, uint32_t a, uint32_t x, uint32_t y) {
  asm volatile("{\n.reg .pred q;\nsetp.ne.b32 q, %3, 0;\n@q st.shared.v2.u32 [%0], {%1,%2};\n}\n" ::"r"(a), "r"(x), "r"(y), "r"(p) : "memory");
}
__device__ __forceinline__ void st_x32(uint32_t* p, uint32_t x) {
  asm volatile("st.relaxed.gpu.global.u32 [%0], %1;" ::"l"(p), "r"(x) : "memory");
}
__device__ __forceinline__ uint32_t nz(uint32_t w) { return max(w, 1u); }
__device__ __forceinline__ uint32_t fu(float x) { return __float_as_uint(x); }
__device__ __forceinline__ float uf(uint32_t x) { return __uint_as_float(x); }

__device__ __forceinline__ void wgmma_ss_n96(float (&d)[48], uint64_t da, uint64_t db, int sc) {
  asm volatile("{\n.reg .pred p;\nsetp.ne.b32 p, %50, 0;\n"
      "wgmma.mma_async.sync.aligned.m64n96k16.f32.bf16.bf16 "
      "{%0,%1,%2,%3,%4,%5,%6,%7,%8,%9,%10,%11,%12,%13,%14,%15,%16,%17,%18,%19,%20,%21,%22,%23,%24,%25,%26,%27,%28,%29,%30,%31,%32,%33,%34,%35,%36,%37,%38,%39,%40,%41,%42,%43,%44,%45,%46,%47}, "
      "%48, %49, p, 1, 1, 0, 1;\n}\n"
      : "+f"(d[0]), "+f"(d[1]), "+f"(d[2]), "+f"(d[3]), "+f"(d[4]), "+f"(d[5]), "+f"(d[6]), "+f"(d[7]),
        "+f"(d[8]), "+f"(d[9]), "+f"(d[10]), "+f"(d[11]), "+f"(d[12]), "+f"(d[13]), "+f"(d[14]), "+f"(d[15]),
        "+f"(d[16]), "+f"(d[17]), "+f"(d[18]), "+f"(d[19]), "+f"(d[20]), "+f"(d[21]), "+f"(d[22]), "+f"(d[23]),
        "+f"(d[24]), "+f"(d[25]), "+f"(d[26]), "+f"(d[27]), "+f"(d[28]), "+f"(d[29]), "+f"(d[30]), "+f"(d[31]),
        "+f"(d[32]), "+f"(d[33]), "+f"(d[34]), "+f"(d[35]), "+f"(d[36]), "+f"(d[37]), "+f"(d[38]), "+f"(d[39]),
        "+f"(d[40]), "+f"(d[41]), "+f"(d[42]), "+f"(d[43]), "+f"(d[44]), "+f"(d[45]), "+f"(d[46]), "+f"(d[47])
      : "l"(da), "l"(db), "r"(sc));
}

__device__ __forceinline__ void wgmma_ss_n128(float (&d)[64], uint64_t da, uint64_t db, int sc) {
  asm volatile("{\n.reg .pred p;\nsetp.ne.b32 p, %66, 0;\n"
      "wgmma.mma_async.sync.aligned.m64n128k16.f32.bf16.bf16 "
      "{%0,%1,%2,%3,%4,%5,%6,%7,%8,%9,%10,%11,%12,%13,%14,%15,%16,%17,%18,%19,%20,%21,%22,%23,%24,%25,%26,%27,%28,%29,%30,%31,%32,%33,%34,%35,%36,%37,%38,%39,%40,%41,%42,%43,%44,%45,%46,%47,%48,%49,%50,%51,%52,%53,%54,%55,%56,%57,%58,%59,%60,%61,%62,%63}, "
      "%64, %65, p, 1, 1, 0, 1;\n}\n"
      : "+f"(d[0]), "+f"(d[1]), "+f"(d[2]), "+f"(d[3]), "+f"(d[4]), "+f"(d[5]), "+f"(d[6]), "+f"(d[7]),
        "+f"(d[8]), "+f"(d[9]), "+f"(d[10]), "+f"(d[11]), "+f"(d[12]), "+f"(d[13]), "+f"(d[14]), "+f"(d[15]),
        "+f"(d[16]), "+f"(d[17]), "+f"(d[18]), "+f"(d[19]), "+f"(d[20]), "+f"(d[21]), "+f"(d[22]), "+f"(d[23]),
        "+f"(d[24]), "+f"(d[25]), "+f"(d[26]), "+f"(d[27]), "+f"(d[28]), "+f"(d[29]), "+f"(d[30]), "+f"(d[31]),
        "+f"(d[32]), "+f"(d[33]), "+f"(d[34]), "+f"(d[35]), "+f"(d[36]), "+f"(d[37]), "+f"(d[38]), "+f"(d[39]),
        "+f"(d[40]), "+f"(d[41]), "+f"(d[42]), "+f"(d[43]), "+f"(d[44]), "+f"(d[45]), "+f"(d[46]), "+f"(d[47]),
        "+f"(d[48]), "+f"(d[49]), "+f"(d[50]), "+f"(d[51]), "+f"(d[52]), "+f"(d[53]), "+f"(d[54]), "+f"(d[55]),
        "+f"(d[56]), "+f"(d[57]), "+f"(d[58]), "+f"(d[59]), "+f"(d[60]), "+f"(d[61]), "+f"(d[62]), "+f"(d[63])
      : "l"(da), "l"(db), "r"(sc));
}

__device__ __forceinline__ void wgmma_rs_n16(float (&d)[8], const uint4& a, uint64_t db, int sc) {
  asm volatile("{\n.reg .pred p;\nsetp.ne.b32 p, %13, 0;\n"
      "wgmma.mma_async.sync.aligned.m64n16k16.f32.bf16.bf16 "
      "{%0,%1,%2,%3,%4,%5,%6,%7}, "
      "{%8,%9,%10,%11}, %12, p, 1, 1, 1;\n}\n"
      : "+f"(d[0]), "+f"(d[1]), "+f"(d[2]), "+f"(d[3]), "+f"(d[4]), "+f"(d[5]), "+f"(d[6]), "+f"(d[7])
      : "r"(a.x), "r"(a.y), "r"(a.z), "r"(a.w), "l"(db), "r"(sc));
}

struct Params {
  const __nv_bfloat16 *logA, *Aim, *Cre, *Cim, *logdt, *Dskip, *x, *wphi, *wo;
  __nv_bfloat16* out;
  uint4* xs;
  long long* ts;
};

__device__ __forceinline__ uint4 tr_row(const uint4 (&v)[8], int i) {
  uint32_t o[4];
#pragma unroll
  for (int m = 0; m < 4; m++) {
    const uint4 &ra = v[2 * m], &rb = v[2 * m + 1];
    const int k = i >> 1;
    const uint32_t xa = k == 0 ? ra.x : k == 1 ? ra.y : k == 2 ? ra.z : ra.w;
    const uint32_t xb = k == 0 ? rb.x : k == 1 ? rb.y : k == 2 ? rb.z : rb.w;
    o[m] = __byte_perm(xa, xb, (i & 1) ? 0x7632 : 0x5410);
  }
  return make_uint4(o[0], o[1], o[2], o[3]);
}

struct cpx { float r, i; };
__device__ __forceinline__ cpx csq(cpx a) { return {a.r * a.r - a.i * a.i, 2.f * (a.r * a.i)}; }
__device__ __forceinline__ cpx polar(float e, float t) {
  const float m = ex2(e);
  return {m * __cosf(t), m * __sinf(t)};
}

struct KgenRaw { unsigned short la, ai, cr, ci, ldt; };
__device__ __forceinline__ KgenRaw kgen_load(const Params& P, int d, int unit, int lane) {
  const int o = d * 128 + unit * 32 + lane;
  return {__ldg((const unsigned short*)P.logA + o), __ldg((const unsigned short*)P.Aim + o), __ldg((const unsigned short*)P.Cre + o),
          __ldg((const unsigned short*)P.Cim + o), __ldg((const unsigned short*)P.logdt + d)};
}
struct hmul { __half2 a, b; };
__device__ __forceinline__ hmul mk_mul(cpx w) { return {__floats2half2_rn(w.r, w.i), __floats2half2_rn(-w.i, w.r)}; }
__device__ __forceinline__ __half2 hcm(__half2 z, const hmul& w) { return __hfma2(__high2half2(z), w.b, __hmul2(__low2half2(z), w.a)); }
__device__ __forceinline__ uint32_t hu(__half2 v) { return *(const uint32_t*)&v; }

__device__ __forceinline__ void kgen_unit(const KgenRaw& r, int lane, uint32_t buf, uint32_t zero, float (&k)[5][4], float& k2048) {
  const float dt = bf_round(expf(bf_lo(r.ldt)));
  const float a2 = -(bf_round(expf(bf_lo(r.la))) * dt) * 1.4426950408889634f;
  const float f = bf_lo(r.ai) * dt;
  const float r128 = f * 20.371832715762604f;
  const uint32_t ex = min(max(__reduce_max_sync(0xffffffffu, max(r.cr & 0x7fffu, r.ci & 0x7fffu)) >> 7, 1u), 253u);
  const float cs = uf((254u - ex) << 23), sc = 2.f * dt * uf(ex << 23);
  const cpx C = {bf_lo(r.cr) * cs, -bf_lo(r.ci) * cs};
  const uint32_t sa = buf + (lane & 7) * 128 + ((((lane >> 3) ^ lane) & 7) << 4);
  const uint32_t lb = buf + (lane >> 3) * 128 + (((lane ^ (lane >> 3)) & 7) << 4);
  const uint32_t la = buf + ((lane >> 3) & 1) * 1024 + (lane >> 4) * 128 + (((lane ^ (lane >> 4)) & 7) << 4);
  auto put = [&](const __half2 (&v)[8], uint32_t off) {
    stsm4(sa + off, hu(v[0]), hu(v[1]), hu(v[2]), hu(v[3]));
    stsm4((sa ^ 64) + off, hu(v[4]), hu(v[5]), hu(v[6]), hu(v[7]));
  };
  uint32_t A[4][4], B[5][2][4];
  auto get = [&](int j, uint32_t off) {
    __syncwarp();
    ldsm4(B[j][0], lb + off);
    ldsm4(B[j][1], (lb ^ 64) + 512 + off);
  };
  auto tile = [&](int j) {
    k[j][0] = k[j][1] = k[j][2] = k[j][3] = 0.f;
#pragma unroll
    for (int s = 0; s < 4; s++) mma_h(k[j], A[s], B[j][s >> 1][2 * (s & 1)], B[j][s >> 1][2 * (s & 1) + 1]);
  };
  auto after = [&](cpx v, uint32_t dep) { return cpx{uf(fu(v.r) ^ (dep & zero)), v.i}; };
  const cpx w1 = polar(a2, f), w128 = polar(a2 * 128.f, (r128 - rintf(r128)) * 6.283185307179586f);
  const cpx w2 = csq(w1), w4 = csq(w2);
  __half2 t0[8], t1[8], t2[8], t3[8], t4[8];
  const hmul m2 = mk_mul(w2), m4 = mk_mul(w4), m128 = mk_mul(w128);
  t0[0] = __floats2half2_rn(1.f, 0.f); t0[1] = __floats2half2_rn(w1.r, w1.i); t0[2] = m2.a; t0[4] = m4.a;
  t0[3] = hcm(t0[1], m2); t0[5] = hcm(t0[1], m4); t0[6] = hcm(t0[2], m4); t0[7] = hcm(t0[3], m4);
  put(t0, 0); get(0, 0);
  t1[0] = m128.a;
#pragma unroll
  for (int i = 1; i < 8; i++) t1[i] = hcm(t0[i], m128);
  put(t1, 1024); get(1, 1024);
  {
    cpx w8 = csq(after(w4, B[0][0][0]));
    w8.i = -w8.i;
    const cpx w16 = csq(w8), w32 = csq(w16), w64 = csq(w32);
    const hmul m8 = mk_mul(w8), m16 = mk_mul(w16), m32 = mk_mul(w32), m64 = mk_mul(w64);
    __half2 a[8];
    a[0] = __floats2half2_rn(C.r, C.i); a[1] = hcm(a[0], m8);
    a[2] = hcm(a[0], m16); a[3] = hcm(a[1], m16);
#pragma unroll
    for (int i = 0; i < 4; i++) a[4 + i] = hcm(a[i], m32);
    put(a, 0);
#pragma unroll
    for (int i = 0; i < 8; i++) a[i] = hcm(a[i], m64);
    put(a, 1024);
    __syncwarp();
#pragma unroll
    for (int s = 0; s < 4; s++) ldsm4(A[s], (la ^ (s << 5)) + s * 256);
  }
  const cpx w256 = csq(after(w128, B[1][0][0]));
  const hmul m256 = mk_mul(w256);
  t2[0] = m256.a;
#pragma unroll
  for (int i = 1; i < 8; i++) t2[i] = hcm((i & 1) ? t1[i & 6] : t0[i & 6], m256);
  put(t2, 0); get(2, 0);
  tile(0); tile(1);
  const cpx w512 = csq(after(w256, A[0][0]));
  const hmul m512 = mk_mul(w512);
  t3[0] = m512.a;
#pragma unroll
  for (int i = 1; i < 8; i++) t3[i] = hcm((i & 2) ? t2[i & 5] : ((i & 1) ? t1[i & 4] : t0[i & 4]), m512);
  put(t3, 1024); get(3, 1024);
  tile(2);
  const cpx w1024 = csq(after(w512, B[2][0][0])), we = csq(w1024);
  const hmul m1024 = mk_mul(w1024);
  t4[0] = m1024.a;
#pragma unroll
  for (int i = 1; i < 8; i++) t4[i] = hcm((i & 4) ? t3[i & 3] : ((i & 2) ? t2[i & 1] : t1[0]), m1024);
  put(t4, 0); get(4, 0);
  tile(3); tile(4);
  k2048 = (C.r * we.r + C.i * we.i) * sc;
#pragma unroll
  for (int j = 0; j < 5; j++) { k[j][0] *= sc; k[j][1] *= sc; k[j][2] *= sc; k[j][3] *= sc; }
}

__device__ __forceinline__ void build_tables(uint32_t tb, int lane, float (&k)[5][4], float k2048) {
  const int g = lane >> 2, c = lane & 3;
  const uint32_t kc = tb + T_KC + 16;
  {
    const uint32_t a0 = kc + 16 * g + 4 * c, a2 = kc + 2 * (256 + 4 * g + c);
    const uint32_t a3 = kc + 2 * (384 + 2 * g + 64 * (c & 1) + (c >> 1)), a4 = kc + 2 * (512 + g + 32 * c);
#pragma unroll
    for (int r = 0; r < 2; r++) {
      sts32(a0 + 128 * r, pack_bf(k[0][2 * r], k[0][2 * r + 1]));
      sts32(a0 + 128 * r + 256, pack_bf(k[1][2 * r], k[1][2 * r + 1]));
      const uint32_t w2 = pack_bf(k[2][2 * r], k[2][2 * r + 1]);
      const uint32_t w3 = pack_bf(k[3][2 * r], k[3][2 * r + 1]);
      const uint32_t w4 = pack_bf(k[4][2 * r], k[4][2 * r + 1]);
      sts16(a2 + 64 * r, w2); sts16(a2 + 64 * r + 128, w2 >> 16);
      sts16(a3 + 32 * r, w3); sts16(a3 + 32 * r + 64, w3 >> 16);
      sts16(a4 + 16 * r, w4); sts16(a4 + 16 * r + 32, w4 >> 16);
    }
  }
  if (lane == 0) { sts16(kc + 2 * 640, pack_bf(k2048, 0.f)); sts16(kc - 2, 0); }
  __syncwarp();
  const uint32_t td = tb + T_D + 32;
  {
    const uint4 v = lds128(kc + 16 * lane);
    const uint32_t pv = lds16(kc + 16 * lane - 2);
    sts128(td + 32 * lane, __byte_perm(v.x, pv, 0x5410), __byte_perm(v.x, v.x, 0x1032), __byte_perm(v.y, v.x, 0x7610),
           __byte_perm(v.y, v.y, 0x1032));
    sts128(td + 32 * lane + 16, __byte_perm(v.z, v.y, 0x7610), __byte_perm(v.z, v.z, 0x1032),
           __byte_perm(v.w, v.z, 0x7610), __byte_perm(v.w, v.w, 0x1032));
  }
  {
    const uint2 v = lds64(kc + 512 + 8 * lane);
    const uint32_t k4 = lds16(kc + 512 + 8 * lane + 8);
    const uint32_t pv = lds16(kc + (lane == 0 ? 510 : 512 + 8 * lane));
    const uint32_t k22 = __byte_perm(v.y, v.y, 0x1010);
    sts128(td + 1024 + 32 * lane, __byte_perm(v.x, pv, 0x5410), __byte_perm(v.x, v.x, 0x1010),
           __byte_perm(v.x, v.x, 0x1032), __byte_perm(v.y, v.x, 0x7610));
    sts128(td + 1024 + 32 * lane + 16, k22, k22, __byte_perm(v.y, v.y, 0x1032), __byte_perm(k4, v.y, 0x7610));
  }
  {
    const uint32_t kk = lds16(kc + 2 * 384);
    const uint32_t w = lane < 3 ? (kk | (kk << 16)) : (lane == 3 ? (kk << 16) : 0u);
    if (lane < 24) sts32(td + 4 * (lane < 16 ? 512 + lane : lane - 24), w);
    const uint32_t lo_ = lds16(kc + 2 * 511), le_ = lds16(kc + 2 * 512);
    const uint32_t ja = tb + T_5 + (lane < 16 ? 4 * lane : 256 + 4 * lane);
    sts32(ja, lane == 16 ? (le_ << 16) : 0u);
    sts32(ja + 384, lane == 16 ? (lo_ << 16) : 0u);
    sts32(tb + (lane < 16 ? T_7 : T_9 - 64) + 4 * lane, 0u);
  }
#pragma unroll
  for (int s = 0; s < 2; s++) {
    const uint32_t b = kc + 2 * (s ? 512 : 384) + 8 * lane;
    const uint2 v = lds64(b);
    uint32_t em = lds16(b - 2), e0 = v.x;
    const uint32_t e4 = lds16(b + 8);
    if (lane == 0) { em = 0; e0 = 0; }
    sts64(tb + (s ? T_7 : T_3) + 64 + 8 * lane, __byte_perm(v.x, em, 0x5432), __byte_perm(v.y, v.x, 0x7632));
    sts64(tb + (s ? T_9 : T_5) + 64 + 8 * lane, __byte_perm(v.y, e0, 0x5410), __byte_perm(e4, v.y, 0x5410));
  }
  __syncwarp();
}

__device__ __forceinline__ uint32_t box2w(int lo, int n, int o) {
  return ((unsigned)(o - lo) < (unsigned)n ? 0x3F80u : 0u) | ((unsigned)(o + 1 - lo) < (unsigned)n ? 0x3F800000u : 0u);
}

#define SPLIT() asm volatile("{\n.reg .pred p;\nsetp.ne.u32 p, %0, 0;\n@p exit;\n}\n" ::"r"(blockIdx.y) : "memory")

__device__ __forceinline__ void conv_channel(uint32_t ub, uint32_t tb, int lane, uint4* ydst) {
  const int g = lane >> 2, c = lane & 3, x = g - 2 * c;
  const int mi = lane >> 3;
  const uint32_t qa = ub + U_PAD + 16 * (lane & 7) + ((mi == 0 || mi == 3) ? U_ODD : 0) - (mi == 0 ? 16 : 0);
  const uint32_t hb = ub + U_PAD + (mi & 1) * U_ODD + 16 * ((lane >> 4) + (lane & 7)) - 16;
  const uint32_t kv = lds16(tb + T_KC + 16 + 2 * 512);
  const int oh = c < 2 ? 8 + 2 * c : 2 * c - 8, og = c < 3 ? 2 * c : -10;
  uint32_t bx[4] = {box2w(g - 4, 9, 2 * c), box2w(g - 3, 7, 2 * c), box2w(g - 4, 9, oh), box2w(g - 3, 7, oh)};
  uint32_t by[4] = {box2w(g - 10, 5, 2 * c - 8), box2w(g - 5, 3, 2 * c - 8), box2w(g - 10, 5, og), box2w(g - 5, 3, og)};
  uint32_t lb0 = ((unsigned)(x + 5) < 2u ? kv : 0u) | ((unsigned)(x + 4) < 2u ? kv << 16 : 0u);
  uint32_t lb1 = ((unsigned)(x - 3) < 2u ? kv : 0u) | ((unsigned)(x - 4) < 2u ? kv << 16 : 0u);
  const int q0 = g - 1, q1 = c < 3 ? g : g - 2;
  uint32_t y0a = ub + U_PAD + (q0 & 1) * U_ODD + 16 * (q0 >> 1) + 4 * c;
  uint32_t y1a = ub + U_PAD + (q1 & 1) * U_ODD + 16 * (q1 >> 1) + 4 * c;
  uint32_t f3[3][4][4];
  {
    const uint32_t fa = tb + T_7 + 4 * (16 + x);
#pragma unroll
    for (int tt = 0; tt < 3; tt++)
#pragma unroll
      for (int D = 0; D < 4; D++) {
        const uint32_t a = fa + (tt == 0 ? 316 : (tt == 1 ? 320 : 0)) + 64 * D;
        f3[tt][D][0] = lds32(a); f3[tt][D][1] = lds32(a + 32); f3[tt][D][2] = lds32(a - 32); f3[tt][D][3] = lds32(a);
      }
  }
#pragma unroll
  for (int i = 0; i < 4; i++) asm volatile("" : "+r"(bx[i]), "+r"(by[i]));
  asm volatile("" : "+r"(lb0), "+r"(lb1), "+r"(y0a), "+r"(y1a));
  mbar_wait(BAR(MB_UFULL));
  mbar_wait(BAR(MB_EMPTY + 15));
  TS(36);
  float acc[16][4];
  {
    uint32_t z09[8], z07[8], zm9[8], zm7[8];
#pragma unroll
    for (int i = 0; i < 8; i++) {
      uint32_t h[4];
      ldsm4(h, hb + 128 * i);
      float y0, y1, y2, y3, w0, w1, w2, w3;
      mma0(y0, y1, y2, y3, bx[0], bx[1], bx[2], bx[3], h[2], c < 2 ? h[3] : h[1]);
      mma0(w0, w1, w2, w3, bx[0], bx[1], bx[2], bx[3], h[1], c < 2 ? h[2] : h[0]);
      z09[i] = pack_bf(y0, y1); z07[i] = pack_bf(y2, y3);
      zm9[i] = pack_bf(w0, w1); zm7[i] = pack_bf(w2, w3);
    }
    float a[4][2][4];
#pragma unroll
    for (int kap = 0; kap < 4; kap++)
#pragma unroll
      for (int sg = 0; sg < 2; sg++)
#pragma unroll
        for (int bk = 3; bk >= kap; bk--) {
          const uint32_t(&q0_)[4] = f3[sg ? 2 : 0][bk - kap];
          const uint32_t(&q1_)[4] = f3[sg ? 2 : 1][bk - kap];
          float(&a0)[4] = a[bk][0];
          float(&a1)[4] = a[bk][1];
          if (sg == 0 && kap == 0) {
            mma0(a0[0], a0[1], a0[2], a0[3], q0_[0], q0_[1], q0_[2], q0_[3], z09[0], z09[1]);
            mma0(a1[0], a1[1], a1[2], a1[3], q1_[0], q1_[1], q1_[2], q1_[3], zm9[0], zm9[1]);
          } else {
            mma(a0[0], a0[1], a0[2], a0[3], q0_[0], q0_[1], q0_[2], q0_[3], sg ? zm7[2 * kap] : z09[2 * kap], sg ? zm7[2 * kap + 1] : z09[2 * kap + 1]);
            mma(a1[0], a1[1], a1[2], a1[3], q1_[0], q1_[1], q1_[2], q1_[3], sg ? z07[2 * kap] : zm9[2 * kap], sg ? z07[2 * kap + 1] : zm9[2 * kap + 1]);
          }
        }
    SPLIT();
#pragma unroll
    for (int i = 0; i < 8; i++) {
      uint32_t h[4];
      ldsm4(h, qa + 128 * i);
      const float ci[4] = {a[i >> 1][0][2 * (i & 1)], a[i >> 1][0][2 * (i & 1) + 1], a[i >> 1][1][2 * (i & 1)], a[i >> 1][1][2 * (i & 1) + 1]};
      mmac(acc[8 + i], h[0], h[1], h[2], h[3], lb0, lb1, ci);
    }
  }
  TS(44);
  {
    uint2 a5[10], a3[10];
    const uint32_t aa = tb + T_5 + 4 * (8 + 2 * g - 2 * c);
#pragma unroll
    for (int m = 0; m < 10; m++) { a5[m] = lds64(aa + 32 * m); a3[m] = lds64(aa + 384 + 32 * m); }
    uint32_t x5[12][2], x3[12][2];
    auto ygen = [&](int kap) {
#pragma unroll
      for (int hh = 0; hh < 2; hh++) {
        float y0, y1, y2, y3;
        mma0(y0, y1, y2, y3, by[0], by[1], by[2], by[3], lds32(y0a + 128 * kap + 64 * hh), lds32(y1a + 128 * kap + 64 * hh));
        x5[kap][hh] = pack_bf(y0, y1);
        x3[kap][hh] = pack_bf(y2, y3);
      }
    };
    ygen(11); ygen(10); ygen(9); ygen(8);
#pragma unroll
    for (int kap = 11; kap >= 0; kap--) {
      if (kap >= 4) ygen(kap - 4);
#pragma unroll
      for (int sg = 0; sg < 2; sg++)
#pragma unroll
        for (int i = 4; i >= 0; i--) {
          const int be = kap + 4 + i;
          if (be <= 15) {
            const uint2 &hi = sg ? a3[2 * i + 1] : a5[2 * i + 1], &lo = sg ? a3[2 * i] : a5[2 * i];
            const uint32_t b0 = sg ? x3[kap][0] : x5[kap][0], b1 = sg ? x3[kap][1] : x5[kap][1];
            if (be < 8 && i == 0 && sg == 0) mma0(acc[be][0], acc[be][1], acc[be][2], acc[be][3], hi.x, hi.y, lo.x, lo.y, b0, b1);
            else mma(acc[be][0], acc[be][1], acc[be][2], acc[be][3], hi.x, hi.y, lo.x, lo.y, b0, b1);
          }
        }
    }
  }
  TS(45);
  {
    const uint32_t st = tb + T_ST + lane * 8;
#pragma unroll
    for (int be = 4; be < 12; be++) sts64(st + 256 * be, pack_bf(acc[be][0], acc[be][1]), pack_bf(acc[be][2], acc[be][3]));
    SPLIT();
    uint32_t F[66], qd[8][4];
    const uint32_t fa = tb + T_D + 32 + 4 * x;
#pragma unroll
    for (int i = 0; i < 32; i++) {
      const int s = 120 - (i >> 2) - 8 * (i & 3);
      uint32_t(&q)[4] = qd[i & 7];
      ldsm4(q, qa + 16 * s);
      const int m = 16 * (i & 3) + 2 * (i >> 2);
      F[m] = lds32(fa + 32 * m); F[m + 1] = lds32(fa + 32 * m + 32);
#pragma unroll
      for (int be = 15; be >= 12; be--) {
        const int de = 8 * be - s;
        if (de >= 0) mma(acc[be][0], acc[be][1], acc[be][2], acc[be][3], q[0], q[1], q[2], q[3], F[2 * de + 1], F[2 * de]);
      }
    }
    F[64] = lds32(fa + 32 * 64); F[65] = lds32(fa + 32 * 65);
    uint32_t qp = qa + 128 * 11, sta = st + 256 * 10;
    uint4* yd = ydst + 7 * 32;
#pragma unroll
    for (int i = 0; i < 6; i++) ldsm4(qd[i], qp - 16 * i);
    uint2 sv = lds64(sta + 256);
    float ci[4] = {bf_lo(sv.x), bf_hi(sv.x), bf_lo(sv.y), bf_hi(sv.y)};
    float T[5][4];
#pragma unroll
    for (int i = 0; i < 16; i++) T[i >> 2][i & 3] = acc[12 + (i >> 2)][i & 3];
    TS(46);
#pragma unroll 1
    for (int bp = 5; bp >= 0; bp--) {
      uint32_t held[2];
#pragma unroll
      for (int o = 1; o >= 0; o--) {
#pragma unroll
        for (int k = 4; k >= 1; k--) mmac(T[k], qd[0][0], qd[0][1], qd[0][2], qd[0][3], F[16 * k + 1], F[16 * k], T[k - 1]);
        mmac(T[0], qd[0][0], qd[0][1], qd[0][2], qd[0][3], F[1], F[0], ci);
        ldsm4(qd[6], qp - 16 * 6);
        ldsm4(qd[7], qp - 16 * 7);
        sv = lds64(sta);
#pragma unroll
        for (int i = 1; i < 8; i++) {
#pragma unroll
          for (int k = 3; k >= 0; k--)
            mma(T[k][0], T[k][1], T[k][2], T[k][3], qd[i][0], qd[i][1], qd[i][2], qd[i][3], F[16 * k + 2 * i + 1], F[16 * k + 2 * i]);
          if (i < 7) ldsm4(qd[i - 1], qp - 128 - 16 * (i - 1));
          if (i == 2) {
            const uint32_t w0 = pack_bf(T[4][0], T[4][1]), w1 = pack_bf(T[4][2], T[4][3]);
            if (o) { held[0] = w0; held[1] = w1; }
            else st_x(yd, nz(w0), w1, held[0], held[1]);
          }
          if (i == 4) {
            if (2 * bp + o <= 4) sv = make_uint2(0, 0);
            ci[0] = bf_lo(sv.x); ci[1] = bf_hi(sv.x); ci[2] = bf_lo(sv.y); ci[3] = bf_hi(sv.y);
          }
        }
        qp -= 128; sta -= 256;
      }
      yd -= 32;
    }
#pragma unroll
    for (int B = 1; B >= 0; B--)
      st_x(ydst + B * 32, nz(pack_bf(T[2 * B][0], T[2 * B][1])), pack_bf(T[2 * B][2], T[2 * B][3]),
           pack_bf(T[2 * B + 1][0], T[2 * B + 1][1]), pack_bf(T[2 * B + 1][2], T[2 * B + 1][3]));
  }
}

__device__ __forceinline__ void dual_exp(const uint32_t* w, uint32_t* e) {
  const float L = 1.44268798828125f;
  uint32_t mx = bmax2(bmax2(w[0], w[1]), bmax2(w[2], w[3]));
  uint32_t mn = bmin2(bmin2(w[0], w[1]), bmin2(w[2], w[3]));
  mx = bmax2(mx, __shfl_xor_sync(0xffffffffu, mx, 1));
  mn = bmin2(mn, __shfl_xor_sync(0xffffffffu, mn, 1));
  mx = bmax2(mx, __shfl_xor_sync(0xffffffffu, mx, 2));
  mn = bmin2(mn, __shfl_xor_sync(0xffffffffu, mn, 2));
  const float mx0 = bf_lo(mx) * -L, mx1 = bf_hi(mx) * -L, mn0 = bf_lo(mn) * L, mn1 = bf_hi(mn) * L;
#pragma unroll
  for (int i = 0; i < 2; i++) {
    const float a0 = bf_lo(w[2 * i]), a1 = bf_hi(w[2 * i]), b0 = bf_lo(w[2 * i + 1]), b1 = bf_hi(w[2 * i + 1]);
    e[2 * i] = pack_bf(ex2(fmaf(a0, L, mx0)), ex2(fmaf(b0, L, mx0)));
    e[2 * i + 1] = pack_bf(ex2(fmaf(a1, L, mx1)), ex2(fmaf(b1, L, mx1)));
    e[4 + 2 * i] = pack_bf(ex2(fmaf(a0, -L, mn0)), ex2(fmaf(b0, -L, mn0)));
    e[5 + 2 * i] = pack_bf(ex2(fmaf(a1, -L, mn1)), ex2(fmaf(b1, -L, mn1)));
  }
}
__device__ __forceinline__ void norm_store(const uint32_t* e, uint32_t dst) {
  float s[4];
  mma0(s[0], s[1], s[2], s[3], e[0], e[1], e[2], e[3], 0x3F803F80u, 0x3F803F80u);
  const uint32_t r = pack_bf(rcp(s[0]), rcp(s[2]));
  const __nv_bfloat162 rr = *(const __nv_bfloat162*)&r;
  uint32_t o[4];
#pragma unroll
  for (int i = 0; i < 4; i++) {
    const __nv_bfloat162 v = __hmul2(*(const __nv_bfloat162*)&e[i], (i & 1) ? __high2bfloat162(rr) : __low2bfloat162(rr));
    o[i] = *(const uint32_t*)&v;
  }
  stsm4(dst, o[0], o[1], o[2], o[3]);
}

__global__ void __launch_bounds__(NTHREADS, 1)
fused_kernel(const Params P, const __grid_constant__ CUtensorMap mx, const __grid_constant__ CUtensorMap mw,
             const __grid_constant__ CUtensorMap mo, const __grid_constant__ CUtensorMap mu,
             const __grid_constant__ CUtensorMap mout, const __grid_constant__ CUtensorMap mw4) {
  constexpr uint32_t sb = SB;
  const int tid = threadIdx.x, lane = tid & 31;
  const int warp = __shfl_sync(0xffffffffu, tid >> 5, 0);
  const int b = blockIdx.x, oct = b >> 3, i8 = b & 7;
  const int rt = oct < 8 ? oct : 15 - oct;
  const int hp = (oct >> 3) * 8 + i8;

  const int wg = warp >> 2, w = warp & 3;
  const int d = b * 4 + ((tid >> 5) & 3);
  if (tid < 384) {
    asm volatile("prefetch.tensormap [%0];" ::"l"(&mu) : "memory");
    asm volatile("prefetch.tensormap [%0];" ::"l"(&mw) : "memory");
    asm volatile("prefetch.tensormap [%0];" ::"l"(&mx) : "memory");
    asm volatile("prefetch.tensormap [%0];" ::"l"(&mw4) : "memory");
  }
  if (warp == 12) {
    if (lane == 0) {
#pragma unroll
      for (int i = 0; i < 9; i++) mbar_init(BAR(i), 1);
      asm volatile("fence.mbarrier_init.release.cluster;" ::: "memory");
    }
    __syncwarp();
    if (lane < 9) mbar_expect(BAR(0) + 8 * lane, lane == 5 ? 65536 : ((lane == 0 || lane > 5) ? 16384 : 28672));
    __syncwarp();
    e_tma3d(sb + OFF_W, &mw, BAR(MB_FULL), hp * 32, 0, 0);
    e_tma2d(sb + OFF_X + 3 * 16384, &mx, BAR(MB_FULL), 0, rt * 256);
  } else if (warp == 13) {
    if (lane == 0) {
#pragma unroll
      for (int i = 9; i < 39; i++) mbar_init(BAR(i), i < MB_EMPTY ? 1 : (i < MB_AUX ? 4 : 5));
      asm volatile("fence.mbarrier_init.release.cluster;" ::: "memory");
    }
    __syncwarp();
    if (lane < 9) mbar_expect(BAR(MB_FULL + 8) + 8 * lane, lane < 8 ? 16384 : 131072);
  }
  const KgenRaw raw = kgen_load(P, d, tid >> 7, lane);
  const unsigned short dsk = __ldg((const unsigned short*)P.Dskip + d);
  if (warp == 12) {
#pragma unroll 1
    for (int kb = 1; kb < 4; kb++) {
      if (kb == U_AT) e_tma5d(sb + OFF_STG0, &mu, BAR(MB_URAW), i8 * 64, oct * 4);
      e_tma3d(sb + OFF_W + kb * 12288, &mw, BAR(MB_FULL) + 8 * kb, hp * 32, kb * 64, 0);
      e_tma2d(sb + OFF_X + (kb < 2 ? kb + 3 : kb - 2) * 16384, &mx, BAR(MB_FULL) + 8 * kb, kb * 64, rt * 256);
    }
    e_prefetch(P.x + (size_t)(rt * 256 + hp * 16) * 512, 16384);
    e_tma4d(sb + OFF_W + 4 * 12288, &mw4, BAR(MB_FULL + 4), hp * 32, 4);
    if (smem_u32(smem_raw) != SB) __trap();
    if (lane == 0) TS1(54);
  }
  const uint32_t tb = sb + OFF_T + w * T_CH;
  float k[5][4], k2048;
  {
    const uint32_t kp = wg == 3 ? sb + OFF_X + 32768 + w * 4096 : tb + (wg & 1) * 2608;
    kgen_unit(raw, lane, wg == 2 ? sb + OFF_STG0 + 16384 + w * 2048 : (kp + 127) & ~127u, blockIdx.y, k, k2048);
    TS(40 + wg);
    k2048 += __shfl_xor_sync(0xffffffffu, k2048, 16);
    k2048 += __shfl_xor_sync(0xffffffffu, k2048, 8);
    if (wg != 2 || (fu(k[0][0]) & fu(k[1][0]) & fu(k[2][0]) & fu(k[3][0]) & fu(k[4][0])) == 0xffffffffu) {
#pragma unroll
      for (int j = 0; j < 5; j++) sts128(kp + j * 512 + lane * 16, fu(k[j][0]), fu(k[j][1]), fu(k[j][2]), fu(k[j][3]));
      if (lane < 8) sts32(kp + 2560 + lane * 4, fu(k2048));
    }
  }
  __syncthreads();
  if (warp >= 12) {
    asm volatile("setmaxnreg.dec.sync.aligned.u32 32;");
    if (warp == 12) {
      nb_sync(NB_KREAD, 160);
      asm volatile("fence.proxy.async.shared::cta;" ::: "memory");
      e_tma2d(sb + OFF_X + 2 * 16384, &mx, BAR(MB_FULL + 4), 256, rt * 256);
      uint32_t slot = sb + OFF_X + 3 * 16384;
#pragma unroll 1
      for (int n = 0; n < 11; n++) {
        mbar_spin(BAR(MB_EMPTY) + 8 * n);
        const int m = n + 5;
        e_tma2d(slot, &mx, BAR(MB_FULL) + 8 * m, (m & 7) * 64, rt * 256 + (m >> 3) * 128);
        slot = slot == sb + OFF_X + 4 * 16384 ? sb + OFF_X : slot + 16384;
        if (n == 7) e_prefetch(P.wo + (size_t)b * 2048, 4096);
      }
#pragma unroll 1
      for (int i = 0; i < 8; i++) {
        mbar_wait(BAR(MB_EMPTY + 10) + 8 * ((0x54332100u >> (4 * i)) & 7));
        const int w0 = (0x54736210u >> (4 * i)) & 7;
        e_tma3d(sb + OFF_W + w0 * 16384, &mo, BAR(MB_WO), 0, w0 * 64, (hp & 3) * 2);
      }
    } else {
      if (warp == 15) {
        const uint4 v0 = __ldg((const uint4*)P.wphi + hp * 64 + lane), v1 = __ldg((const uint4*)P.wphi + hp * 64 + 32 + lane);
        sts128(sb + OFF_PHI + (lane & 1) * 256 + (lane >> 1) * 16, v0.x, v0.y, v0.z, v0.w);
        sts128(sb + OFF_PHI + 512 + (lane & 1) * 256 + (lane >> 1) * 16, v1.x, v1.y, v1.z, v1.w);
        asm volatile("fence.proxy.async.shared::cta;" ::: "memory");
        __syncwarp();
        if (lane == 0) mbar_arrive(BAR(MB_AUX));
        mbar_wait(BAR(MB_EMPTY + ZERO_STEP));
        uint4* py = P.xs + X_Y + b * 1024 + lane;
#pragma unroll 1
        for (int i = 0; i < 1024; i += 32) st_x(py + i, 0, 0, 0, 0);
        nb_arrive(NB_YZ, 160);
        nb_arrive(NB_ODONE, 320);
        if (lane == 0) TS1(55);
        return;
      }
      uint32_t* const cnt = (uint32_t*)(P.xs + X_CNT) + (warp == 13 ? i8 : 8 + rt) * 32;
      const unsigned target = (ld_x32(cnt) & ~15u) + 16;
      if (warp == 13) {
        uint4* pp = P.xs + X_PART + (hp * 8 + rt) * 144 + lane;
#pragma unroll 1
        for (int i = 0; i < 144; i += 32) if (i + lane < 144) st_x(pp + i, 0, 0, 0, 0);
      }
      nb_sync(warp == 13 ? NB_INIT : NB_ODONE, warp == 13 ? 160 : 320);
      if (lane == 0) TS1(warp == 13 ? 49 : 56);
      asm volatile("fence.proxy.async.shared::cta;" ::: "memory");
      if (lane == 0) asm volatile("red.release.gpu.global.add.u32 [%0], 1;" ::"l"(cnt) : "memory");
      if (lane == 0) TS1(warp == 13 ? 50 : 57);
      const uint32_t* pc = (warp == 13 && (lane & 1)) ? (uint32_t*)(P.xs + X_CNT) + (b >> 4) * 32 : cnt;
#pragma unroll 1
      for (int i = 0; i < SPIN_MAX; i++) {
        unsigned v;
        asm volatile("ld.acquire.gpu.global.u32 %0, [%1];" : "=r"(v) : "l"(pc) : "memory");
        if (__all_sync(0xffffffffu, (int)(v - target) >= 0)) break;
      }
      if (lane == 0) TS1(warp == 13 ? 51 : 58);
      asm volatile("fence.proxy.async.global;" ::: "memory");
      if (warp == 13) {
        mbar_wait(BAR(MB_EMPTY + 11));
        e_expect(BAR(MB_UFULL), 4 * U_CH);
        e_bulk(sb + OFF_U, P.xs + X_UT + b * (U_CH / 4), 4 * U_CH, BAR(MB_UFULL));
      } else {
        const uint4* src = P.xs + X_O + (rt * 4 + (hp >> 2)) * 4096;
        e_expect(BAR(MB_OA), 14336);
        e_bulk(sb + OFF_STG0, src + 3200, 14336, BAR(MB_OA));
        e_expect(BAR(MB_OC), 32768);
        e_bulk(sb + OFF_X + 32768, src, 32768, BAR(MB_OC));
        nb_sync(NB_BDONE, 288);
        asm volatile("fence.proxy.async.shared::cta;" ::: "memory");
        e_expect(BAR(MB_OB), 18432);
        e_bulk(sb + OFF_U, src + 2048, 18432, BAR(MB_OB));
      }
    }
    return;
  }

  asm volatile("setmaxnreg.inc.sync.aligned.u32 160;");
  const int t = tid & 127;
  const int g = lane >> 2, c = lane & 3;
  {
    if (wg == 2) {
#pragma unroll 1
      for (int q = 0; q < 3; q++) {
        const uint32_t src = q ? tb + (q - 1) * 2608 : sb + OFF_X + 32768 + w * 4096;
#pragma unroll
        for (int j = 0; j < 5; j++) {
          const uint4 v = lds128(src + j * 512 + lane * 16);
          k[j][0] += uf(v.x); k[j][1] += uf(v.y); k[j][2] += uf(v.z); k[j][3] += uf(v.w);
        }
        k2048 += uf(lds32(src + 2560 + (lane & 7) * 4));
        if (q == 0) nb_arrive(NB_KREAD, 160);
      }
#pragma unroll
      for (int o2 = 4; o2; o2 >>= 1) k2048 += __shfl_xor_sync(0xffffffffu, k2048, o2);
      if (lane == 0) k[0][0] += bf_lo(dsk);
      __syncwarp();
      TS(34);
      build_tables(tb, lane, k, k2048);
      TS(35);
      nb_sync(NB_YZ, 160);
      uint4* const g_y = P.xs + X_Y;
      conv_channel(sb + OFF_U + w * U_CH, tb, lane, g_y + (size_t)d * 256 + lane);
      nb_arrive(NB_BDONE, 288);
      TS(37);
      mbar_wait(BAR(MB_OA));
      const int lam = w * 8 + g;
      const uint4* src = g_y + (size_t)(oct * 32 + c * 8) * 256 + i8 * 32 + lam;
      uint4 v[8];
#pragma unroll 1
      for (int it = 0; it < SPIN_MAX; it++) {
        uint32_t m = 0xffffffffu;
#pragma unroll
        for (int i = 0; i < 8; i++) v[i] = ld_x(src + i * 256);
#pragma unroll
        for (int i = 0; i < 8; i++) m = min(m, v[i].x);
        if (__all_sync(0xffffffffu, m != 0)) break;
      }
      __nv_bfloat16* dst = P.out + (size_t)(i8 * 256 + (lam >> 2) * 16 + (lam & 3) * 2) * 1024 + 512 + oct * 32 + c * 8;
#pragma unroll
      for (int i = 0; i < 8; i++) *(uint4*)(dst + (size_t)((i >> 2) * 128 + ((i >> 1) & 1) * 8 + (i & 1)) * 1024) = tr_row(v, i);
      TS(38);
      GT(63);
      if (w == 0) TSDUMP(32);
      return;
    }
    if (wg == 1) {
      mbar_wait(BAR(MB_URAW));
      TS(48);
      uint4* dst = P.xs + X_UT + (i8 * 64 + g) * (U_CH / 16) + (c & 1) * (U_ODD / 16) + U_PAD / 16 + oct * 8 + w * 2 + (c >> 1);
      uint32_t r[8][4];
#pragma unroll
      for (int i = 0; i < 8; i++) ldsm4t(r[i], sb + OFF_STG0 + w * 4096 + lane * 128 + (((i ^ lane) & 7) << 4));
#pragma unroll
      for (int i = 0; i < 8; i++) dst[i * (U_CH / 2)] = make_uint4(r[i][0], r[i][1], r[i][2], r[i][3]);
      nb_arrive(NB_INIT, 160);
      if (lane == 0) mbar_arrive(BAR(MB_AUX));
      mbar_wait(BAR(MB_EMPTY + 4));
      mbar_spin(BAR(MB_EMPTY + 6));
    }
    TS(wg * 16 + 1);
  }

  float acc[2][48];
  {
    uint32_t fb = BAR(MB_FULL) + 64 * wg;
    uint32_t da = (uint32_t)mkdesc(sb + OFF_X, 16, 0, 0) + (wg ? 1024 : 3072), db = (uint32_t)mkdesc(sb + OFF_W, 4096, 0, 0);
    constexpr uint64_t ha = mkdesc(0, 0, 1024, 1), hb = mkdesc(0, 0, 512, 2);
#pragma unroll 1
    for (int kb = 0; kb < 8; kb++) {
      mbar_spin(fb);
      if (kb == 0) TS(wg * 16 + 2);
      WG_FENCE();
#pragma unroll
      for (int k = 0; k < 4; k++) {
        wgmma_ss_n96(acc[0], ha | (da + 2 * k), hb | (db + 64 * k), k ? 1 : kb);
        wgmma_ss_n96(acc[1], ha | (da + 2 * k + 512), hb | (db + 64 * k), k ? 1 : kb);
      }
      WG_COMMIT();
      WG_WAIT(1);
      if (kb > 0 && lane == 0) mbar_arrive(fb + 8 * (MB_EMPTY - MB_FULL - 1));
      fb += 8; db += 768;
      da = da == (uint32_t)mkdesc(sb + OFF_X + 65536, 16, 0, 0) ? da - 4096 : da + 1024;
    }
    WG_WAIT(0);
    if (lane == 0) mbar_arrive(fb + 8 * (MB_EMPTY - MB_FULL - 1));
    mbar_spin(fb + 8 * (MB_EMPTY - MB_FULL - 1));
  }
  TS(wg * 16 + 3);

  constexpr uint32_t stg0 = sb + OFF_STG0, stg1 = sb + OFF_X + 32768;
  const uint32_t sl = (wg ? stg1 : stg0) + w * 3072 + lane * 16;
  uint32_t pw[32], eq[32];
  {
    uint4 af[8];
#pragma unroll
    for (int u = 0; u < 8; u++) {
      const float* a = acc[(u >> 1) & 1] + (u < 4 ? 16 : 0) + 8 * (u & 1);
      af[u] = make_uint4(pack_bf(a[0], a[1]), pack_bf(a[2], a[3]), pack_bf(a[4], a[5]), pack_bf(a[6], a[7]));
    }
    mbar_wait(BAR(MB_AUX));
    float p[8][8];
    WG_FENCE();
#pragma unroll
    for (int u = 0; u < 8; u++) wgmma_rs_n16(p[u], af[u], mkdesc(sb + OFF_PHI + (u & 1) * 512, 128, 256, 0), 0);
    WG_COMMIT();
#pragma unroll
    for (int i = 0; i < 4; i++) {
      const float* a = acc[i >> 1] + 32 + 8 * (i & 1);
      stsm4(sl + (i >> 1) * 12288 + 2048 + (i & 1) * 512, pack_bf(a[0], a[1]), pack_bf(a[2], a[3]), pack_bf(a[4], a[5]), pack_bf(a[6], a[7]));
    }
    WG_WAIT(0);
#pragma unroll
    for (int u = 0; u < 8; u++) {
      pw[4 * u] = pack_bf(p[u][0], p[u][2]); pw[4 * u + 1] = pack_bf(p[u][1], p[u][3]);
      pw[4 * u + 2] = pack_bf(p[u][4], p[u][6]); pw[4 * u + 3] = pack_bf(p[u][5], p[u][7]);
    }
  }
  uint32_t ek[32];
  if (wg == 0) {
#pragma unroll
    for (int i = 0; i < 16; i++) { const uint32_t x = pw[i]; pw[i] = pw[16 + i]; pw[16 + i] = x; }
  }
#pragma unroll 1
  for (int it = 0; it < 2; it++) {
#pragma unroll
    for (int i = 0; i < 32; i++) ek[i] = eq[i];
#pragma unroll
    for (int u = 0; u < 4; u++) dual_exp(pw + 4 * u, eq + 8 * u);
    if (it != wg) {
      TS(wg * 16 + 12);
      mbar_wait(BAR(MB_EMPTY + 15));
#pragma unroll
      for (int i = 0; i < 8; i++) norm_store(eq + 4 * i, sl + (i >> 2) * 12288 + (i & 3) * 512);
      if (wg) nb_arrive(NB_ST0, 256);
    }
#pragma unroll
    for (int i = 0; i < 16; i++) pw[i] = pw[i + 16];
  }
  TS(wg * 16 + 4);
  uint4* const g_part = P.xs + X_PART;
  uint4* const g_o = P.xs + X_O;
  const uint32_t kvs = stg0;
  if (wg == 0) {
#pragma unroll
    for (int i = 0; i < 32; i++) eq[i] = ek[i];
    nb_sync(NB_WG0, 128);
    mbar_wait(BAR(MB_UFULL));
    float kv[12], kw[12];
#pragma unroll
    for (int i = 0; i < 12; i++) kv[i] = kw[i] = 0.f;
    const int mi = lane >> 3;
    const uint32_t ao = w * 512 + (lane & 7) * 16 + ((mi & 1) * 2 + (mi >> 1)) * 128, bo = 2048 + (w >> 1) * 512 + lane * 16;
#pragma unroll 1
    for (int j = 0; j < 2; j++) {
      if (j) nb_sync(NB_ST0, 256);
      const uint32_t sg = j ? stg1 : stg0;
      uint32_t a[8][4], bb[8][4];
#pragma unroll
      for (int s = 0; s < 8; s++) { ldsm4t(a[s], sg + s * 3072 + ao); ldsm4t(bb[s], sg + s * 3072 + bo); }
#pragma unroll
      for (int s = 0; s < 8; s++) {
        float* o = (s & 1) ? kw : kv;
        mma(o[0], o[1], o[2], o[3], a[s][0], a[s][1], a[s][2], a[s][3], bb[s][0], bb[s][1]);
        mma(o[4], o[5], o[6], o[7], a[s][0], a[s][1], a[s][2], a[s][3], bb[s][2], bb[s][3]);
        mma(o[8], o[9], o[10], o[11], a[s][0], a[s][1], a[s][2], a[s][3], 0x3F803F80u, 0x3F803F80u);
      }
    }
#pragma unroll
    for (int i = 0; i < 12; i++) kv[i] += kw[i];
    uint4* pp = g_part + (size_t)(hp * 8 + rt) * 144;
    st_x(pp + t, nz(pack_bf(kv[0], kv[1])), pack_bf(kv[2], kv[3]), pack_bf(kv[4], kv[5]), pack_bf(kv[6], kv[7]));
    if (c < 2) st_x32((uint32_t*)(pp + 128) + w * 16 + c * 8 + g, nz(fu(c ? kv[10] : kv[8])));
    TS(5);
    const uint4* ps = g_part + (size_t)hp * 8 * 144 + t;
    const uint32_t* zs = (const uint32_t*)(g_part + (size_t)(hp * 8 + (lane >> 4) * 4) * 144 + 128) + w * 16 + (lane & 15);
    uint4 v[8];
    uint32_t zv[4];
#pragma unroll 1
    for (int it = 0; it < SPIN_MAX; it++) {
#pragma unroll
      for (int i = 0; i < 8; i++) v[i] = ld_x(ps + i * 144);
#pragma unroll
      for (int i = 0; i < 4; i++) zv[i] = ld_x32(zs + i * 576);
      uint32_t m = min(min(zv[0], zv[1]), min(zv[2], zv[3]));
#pragma unroll
      for (int i = 0; i < 8; i++) m = min(m, v[i].x);
      if (__all_sync(0xffffffffu, m != 0)) break;
    }
    float s4[4][4];
#pragma unroll
    for (int i = 0; i < 4; i++) s4[i][0] = s4[i][1] = s4[i][2] = s4[i][3] = 0.f;
    const uint32_t eye = (g >> 1) == c ? ((g & 1) ? 0x3F800000u : 0x3F80u) : 0u;
#pragma unroll
    for (int r = 0; r < 8; r++) {
      mma_k8(s4[(r & 1) * 2], v[r].x, v[r].y, eye);
      mma_k8(s4[(r & 1) * 2 + 1], v[r].z, v[r].w, eye);
    }
    float s[8];
#pragma unroll
    for (int i = 0; i < 8; i++) s[i] = s4[i >> 2][i & 3] + s4[2 + (i >> 2)][i & 3];
    float zsum = (uf(zv[0]) + uf(zv[1])) + (uf(zv[2]) + uf(zv[3]));
    zsum += __shfl_xor_sync(0xffffffffu, zsum, 16);
    stsm4(kvs + w * 512 + lane * 16, pack_bf(s[0], s[1]), pack_bf(s[2], s[3]), pack_bf(s[4], s[5]), pack_bf(s[6], s[7]));
    sts16(kvs + 2048 + (lane >> 4) * 128 + (w * 16 + (lane & 15)) * 2, lane < 16 ? pack_bf(zsum, 0.f) : 0x3F80u);
    TS(6);
  }
  nb_sync(NB_KV, 256);
  {
    uint32_t kb_[4][4], zb[8];
#pragma unroll
    for (int i = 0; i < 4; i++) ldsm4t(kb_[i], kvs + i * 512 + lane * 16);
#pragma unroll
    for (int i = 0; i < 8; i++) zb[i] = lds32(kvs + 2048 + (g & 1) * 128 + i * 16 + c * 4);
    uint32_t* od = (uint32_t*)(g_o + (size_t)((rt * 4 + wg * 2) * 32 + hp * 2) * 128) + w * 64 + lane;
#pragma unroll
    for (int mt = 0; mt < 2; mt++) {
#pragma unroll
      for (int h = 0; h < 2; h++) {
        const uint32_t* e = eq + 16 * mt + 8 * h;
        float n[8], nm[8], dp[4], dm[4];
        mma0(dp[0], dp[1], dp[2], dp[3], e[0], e[1], e[2], e[3], zb[4 * h], zb[4 * h + 1]);
        mma0(dm[0], dm[1], dm[2], dm[3], e[4], e[5], e[6], e[7], zb[4 * h + 2], zb[4 * h + 3]);
        mma0(n[0], n[1], n[2], n[3], e[0], e[1], e[2], e[3], kb_[2 * h][0], kb_[2 * h][1]);
        mma0(nm[0], nm[1], nm[2], nm[3], e[4], e[5], e[6], e[7], kb_[2 * h + 1][0], kb_[2 * h + 1][1]);
        mma0(n[4], n[5], n[6], n[7], e[0], e[1], e[2], e[3], kb_[2 * h][2], kb_[2 * h][3]);
        mma0(nm[4], nm[5], nm[6], nm[7], e[4], e[5], e[6], e[7], kb_[2 * h + 1][2], kb_[2 * h + 1][3]);
        const float q0 = dp[1] * rcp(dm[1]), q1 = dp[3] * rcp(dm[3]);
        const float r0 = rcp(fmaf(dm[0], q0, fmaf(dp[1], 1e-6f, dp[0]))), r1 = rcp(fmaf(dm[2], q1, fmaf(dp[3], 1e-6f, dp[2])));
#pragma unroll
        for (int i = 0; i < 8; i++) n[i] = fmaf(nm[i], (i & 2) ? q1 : q0, n[i]);
        od[h * 512] = pack_bf(n[0] * r0, n[1] * r0);
        od[h * 512 + 32] = pack_bf(n[2] * r1, n[3] * r1);
        od[h * 512 + 256] = pack_bf(n[4] * r0, n[5] * r0);
        od[h * 512 + 288] = pack_bf(n[6] * r1, n[7] * r1);
      }
      od += 16384;
    }
  }
  TS(wg * 16 + 7);
  nb_arrive(NB_ODONE, 320);
  if (wg) { if (w == 0) TSDUMP(16); return; }
  mbar_wait(BAR(MB_WO));
  mbar_wait(BAR(MB_OA));
  TS(8);
  nb_sync(NB_BDONE, 288);
  TS(9);
  float oc[64];
  {
    constexpr uint64_t ha = mkdesc(0, 0, 128, 0), hb = mkdesc(0, 0, 1024, 1);
    constexpr uint32_t da0 = (uint32_t)mkdesc(stg1, 1024, 0, 0), db0 = (uint32_t)mkdesc(sb + OFF_W, 8192, 0, 0);
#pragma unroll 1
    for (int j = 0; j < 8; j++) {
      const int kb = (j + 7) & 7;
      if ((j & 3) == 1) mbar_spin(j == 1 ? BAR(MB_OC) : BAR(MB_OB));
      WG_FENCE();
#pragma unroll
      for (int k = 0; k < 4; k++) wgmma_ss_n128(oc, ha | (da0 + 512 * kb + 128 * k), hb | (db0 + 1024 * kb + 128 * k), k ? 1 : j);
      WG_COMMIT();
    }
    WG_WAIT(0);
  }
  TS(10);
  nb_sync(NB_WG0, 128);
  const uint32_t ot = sb + OFF_W + w * 4096;
#pragma unroll
  for (int i = 0; i < 16; i += 2)
    stsm4(ot + (i >> 3) * 2048 + (lane & 15) * 128 + (((i + (lane >> 4)) ^ lane) & 7) * 16, pack_bf(oc[4 * i], oc[4 * i + 1]),
          pack_bf(oc[4 * i + 2], oc[4 * i + 3]), pack_bf(oc[4 * i + 4], oc[4 * i + 5]), pack_bf(oc[4 * i + 6], oc[4 * i + 7]));
  asm volatile("fence.proxy.async.shared::cta;" ::: "memory");
  __syncwarp();
  e_store3d(&mout, ot, (rt * 4 + (hp >> 2)) * 64 + w * 16, (hp & 3) * 2);
  TS(wg * 16 + 11);
  GT(61 + wg);
  if (w == 0) TSDUMP(0);
  if (w == 1) TSDUMP(48);
}

typedef CUresult (*EncodeFn)(CUtensorMap*, CUtensorMapDataType, cuuint32_t, void*, const cuuint64_t*, const cuuint64_t*,
                             const cuuint32_t*, const cuuint32_t*, CUtensorMapInterleave, CUtensorMapSwizzle,
                             CUtensorMapL2promotion, CUtensorMapFloatOOBfill);

}

extern "C" void kernel_launch(void* const* d_in, const int* in_sizes, int n_in, void* d_out, int out_size) {
  (void)in_sizes; (void)n_in; (void)out_size;
  void* fn = nullptr;
  cudaDriverEntryPointQueryResult qr;
  cudaGetDriverEntryPoint("cuTensorMapEncodeTiled", &fn, cudaEnableDefault, &qr);
  EncodeFn enc = (EncodeFn)fn;
  CUtensorMap mx, mw, mo, mu, mout, mw4;
  const cuuint32_t es[5] = {1, 1, 1, 1, 1};
  {
    cuuint64_t dims[2] = {512, 2048}, st[1] = {1024};
    cuuint32_t box[2] = {64, 128};
    enc(&mx, CU_TENSOR_MAP_DATA_TYPE_BFLOAT16, 2, d_in[0], dims, st, box, es, CU_TENSOR_MAP_INTERLEAVE_NONE,
        CU_TENSOR_MAP_SWIZZLE_128B, CU_TENSOR_MAP_L2_PROMOTION_L2_128B, CU_TENSOR_MAP_FLOAT_OOB_FILL_NONE);
  }
  {
    cuuint64_t dims[3] = {512, 512, 3}, st[2] = {3072, 1024};
    cuuint32_t box[3] = {32, 64, 3};
    enc(&mw, CU_TENSOR_MAP_DATA_TYPE_BFLOAT16, 3, d_in[1], dims, st, box, es, CU_TENSOR_MAP_INTERLEAVE_NONE,
        CU_TENSOR_MAP_SWIZZLE_64B, CU_TENSOR_MAP_L2_PROMOTION_L2_128B, CU_TENSOR_MAP_FLOAT_OOB_FILL_NONE);
  }
  {
    cuuint64_t dims[3] = {64, 512, 8}, st[2] = {1024, 128};
    cuuint32_t box[3] = {64, 64, 2};
    enc(&mo, CU_TENSOR_MAP_DATA_TYPE_BFLOAT16, 3, d_in[3], dims, st, box, es, CU_TENSOR_MAP_INTERLEAVE_NONE,
        CU_TENSOR_MAP_SWIZZLE_128B, CU_TENSOR_MAP_L2_PROMOTION_L2_128B, CU_TENSOR_MAP_FLOAT_OOB_FILL_NONE);
  }
  {
    cuuint64_t dims[5] = {512, 2, 4, 4, 64}, st[4] = {1024, 8192, 2048, 32768};
    cuuint32_t box[5] = {64, 2, 4, 4, 4};
    enc(&mu, CU_TENSOR_MAP_DATA_TYPE_BFLOAT16, 5, d_in[4], dims, st, box, es, CU_TENSOR_MAP_INTERLEAVE_NONE,
        CU_TENSOR_MAP_SWIZZLE_128B, CU_TENSOR_MAP_L2_PROMOTION_L2_128B, CU_TENSOR_MAP_FLOAT_OOB_FILL_NONE);
  }
  {
    cuuint64_t dims[3] = {64, 2048, 16}, st[2] = {2048, 128};
    cuuint32_t box[3] = {64, 16, 2};
    enc(&mout, CU_TENSOR_MAP_DATA_TYPE_BFLOAT16, 3, d_out, dims, st, box, es, CU_TENSOR_MAP_INTERLEAVE_NONE,
        CU_TENSOR_MAP_SWIZZLE_128B, CU_TENSOR_MAP_L2_PROMOTION_NONE, CU_TENSOR_MAP_FLOAT_OOB_FILL_NONE);
  }
  {
    cuuint64_t dims[4] = {512, 64, 3, 8}, st[3] = {3072, 1024, 64 * 3072};
    cuuint32_t box[4] = {32, 64, 3, 4};
    enc(&mw4, CU_TENSOR_MAP_DATA_TYPE_BFLOAT16, 4, d_in[1], dims, st, box, es, CU_TENSOR_MAP_INTERLEAVE_NONE,
        CU_TENSOR_MAP_SWIZZLE_64B, CU_TENSOR_MAP_L2_PROMOTION_L2_128B, CU_TENSOR_MAP_FLOAT_OOB_FILL_NONE);
  }
  Params P;
  P.x = (const __nv_bfloat16*)d_in[0];
  P.wphi = (const __nv_bfloat16*)d_in[2];
  P.wo = (const __nv_bfloat16*)d_in[3];
  P.logA = (const __nv_bfloat16*)d_in[5];
  P.Aim = (const __nv_bfloat16*)d_in[6];
  P.Cre = (const __nv_bfloat16*)d_in[7];
  P.Cim = (const __nv_bfloat16*)d_in[8];
  P.logdt = (const __nv_bfloat16*)d_in[9];
  P.Dskip = (const __nv_bfloat16*)d_in[10];
  P.out = (__nv_bfloat16*)d_out;
  cudaGetSymbolAddress((void**)&P.xs, g_x);
  P.ts = nullptr;
  cudaFuncSetAttribute(fused_kernel, cudaFuncAttributeMaxDynamicSharedMemorySize, SMEM_BYTES);
  fused_kernel<<<NCTA, NTHREADS, SMEM_BYTES>>>(P, mx, mw, mo, mu, mout, mw4);
}
```

```cpp
#include <cuda_runtime.h>
#include <cuda_bf16.h>
#include <cuda_fp16.h>
#include <cuda.h>
#include <stdint.h>

#define DBG_TS 0

namespace {

constexpr int NTHREADS = 512;
constexpr int NCTA = 128;
constexpr int OFF_W = 0;
constexpr int OFF_X = 98304;
constexpr int OFF_U = OFF_X + 65536;
constexpr int U_CH = 4416, U_ODD = 2240, U_PAD = 128;
constexpr int OFF_STG0 = OFF_U + 18432;
constexpr int OFF_T = OFF_STG0 + 24576;
constexpr int T_CH = 5216;
constexpr int T_D = 0;
constexpr int T_5 = 2144;
constexpr int T_3 = T_5 + 384;
constexpr int T_7 = T_5 + 1024;
constexpr int T_9 = T_7 + 320;
constexpr int T_KC = T_9 + 320;
constexpr int T_ST = T_5 - 1024;
constexpr int OFF_PHI = OFF_T + 4 * T_CH;
constexpr int OFF_BAR = OFF_PHI + 1024;
constexpr int SMEM_BYTES = OFF_BAR + 512 + 256 * DBG_TS;
constexpr uint32_t SB = 1024;
static_assert(T_KC + 2 * 656 <= T_CH, "table size");
static_assert(SMEM_BYTES <= 232448, "smem");
constexpr int MB_URAW = 0, MB_FULL = 1  , MB_WO = 17, MB_UFULL = 18, MB_OA = 19, MB_OB = 20, MB_OC = 21,
              MB_EMPTY = 22  , MB_AUX = 38;
__host__ __device__ constexpr uint32_t BAR(int i) { return SB + OFF_BAR + 8 * i; }
constexpr int NB_WG0 = 1, NB_ODONE = 2, NB_ST0 = 3  , NB_KV = 5, NB_YZ = 6, NB_INIT = 7, NB_PREP = 8, NB_PROD = 9, NB_KREAD = 10, NB_BDONE = 11, NB_ZERO = 12;
#define U_AT 2
#define ZERO_STEP 15
constexpr int SPIN_MAX = 1 << 16;

constexpr int X_CNT = 0;
constexpr int X_PART = 128;
constexpr int X_O = X_PART + 16 * 8 * 144;
constexpr int X_Y = X_O + 32 * 32 * 128;
constexpr int X_UT = X_Y + 512 * 8 * 32;
constexpr int X_SIZE = X_UT + 512 * (U_CH / 16);
__device__ __align__(128) uint4 g_x[X_SIZE];
extern __shared__ uint8_t smem_raw[];
#define TS(i) do {} while (0)
#define TS1(i) do {} while (0)
#define GT(i) do {} while (0)
#define TSDUMP(base) do {} while (0)

__device__ __forceinline__ uint32_t smem_u32(const void* p) { return (uint32_t)__cvta_generic_to_shared(p); }
__device__ __forceinline__ void mbar_arrive(uint32_t b) {
  asm volatile("mbarrier.arrive.shared::cta.b64 _, [%0];" ::"r"(b) : "memory");
}
__device__ __forceinline__ void mbar_wait(uint32_t b) {
  uint32_t done = 0;
#pragma unroll 1
  for (int i = 0; i < SPIN_MAX && !done; i++) {
    asm volatile("{\n.reg .pred p;\nmbarrier.try_wait.parity.shared::cta.b64 p, [%1], 0, 4000;\nselp.u32 %0, 1, 0, p;\n}\n"
                 : "=r"(done) : "r"(b) : "memory");
  }
}
__device__ __forceinline__ void mbar_spin(uint32_t b) {
  uint32_t done = 0;
#pragma unroll 1
  for (int i = 0; i < (SPIN_MAX << 4) && !done; i++) {
    asm volatile("{\n.reg .pred p;\nmbarrier.try_wait.parity.shared::cta.b64 p, [%1], 0;\nselp.u32 %0, 1, 0, p;\n}\n"
                 : "=r"(done) : "r"(b) : "memory");
  }
}
__device__ __forceinline__ void mbar_init(uint32_t b, int n) {
  asm volatile("mbarrier.init.shared::cta.b64 [%0], %1;" ::"r"(b), "r"(n) : "memory");
}
__device__ __forceinline__ void mbar_expect(uint32_t b, int bytes) {
  asm volatile("mbarrier.arrive.expect_tx.shared::cta.b64 _, [%0], %1;" ::"r"(b), "r"(bytes) : "memory");
}
__device__ __forceinline__ void nb_sync(int id, int n) { asm volatile("bar.sync %0, %1;" ::"r"(id), "r"(n) : "memory"); }
__device__ __forceinline__ void nb_arrive(int id, int n) { asm volatile("bar.arrive %0, %1;" ::"r"(id), "r"(n) : "memory"); }
#define ELECT "{\n.reg .pred p;\nelect.sync _|p, 0xffffffff;\n@p "
__device__ __forceinline__ void e_expect(uint32_t b, int bytes) {
  asm volatile(ELECT "mbarrier.arrive.expect_tx.shared::cta.b64 _, [%0], %1;\n}\n" ::"r"(b), "r"(bytes) : "memory");
}
__device__ __forceinline__ void e_tma2d(uint32_t dst, const CUtensorMap* m, uint32_t bar, int c0, int c1) {
  asm volatile(ELECT "cp.async.bulk.tensor.2d.shared::cluster.global.mbarrier::complete_tx::bytes [%0], [%1, {%3,%4}], [%2];\n}\n"
               ::"r"(dst), "l"(m), "r"(bar), "r"(c0), "r"(c1) : "memory");
}
__device__ __forceinline__ void e_tma3d(uint32_t dst, const CUtensorMap* m, uint32_t bar, int c0, int c1, int c2) {
  asm volatile(ELECT "cp.async.bulk.tensor.3d.shared::cluster.global.mbarrier::complete_tx::bytes [%0], [%1, {%3,%4,%5}], [%2];\n}\n"
               ::"r"(dst), "l"(m), "r"(bar), "r"(c0), "r"(c1), "r"(c2) : "memory");
}
__device__ __forceinline__ void e_tma4d(uint32_t dst, const CUtensorMap* m, uint32_t bar, int c0, int c3) {
  asm volatile(ELECT "cp.async.bulk.tensor.4d.shared::cluster.global.mbarrier::complete_tx::bytes [%0], [%1, {%3,%5,%5,%4}], [%2];\n}\n"
               ::"r"(dst), "l"(m), "r"(bar), "r"(c0), "r"(c3), "r"(0) : "memory");
}
__device__ __forceinline__ void e_tma5d(uint32_t dst, const CUtensorMap* m, uint32_t bar, int c0, int c4) {
  asm volatile(ELECT "cp.async.bulk.tensor.5d.shared::cluster.global.mbarrier::complete_tx::bytes [%0], [%1, {%3,%5,%5,%5,%4}], [%2];\n}\n"
               ::"r"(dst), "l"(m), "r"(bar), "r"(c0), "r"(c4), "r"(0) : "memory");
}
__device__ __forceinline__ void e_bulk(uint32_t dst, const void* src, int bytes, uint32_t bar) {
  asm volatile(ELECT "cp.async.bulk.shared::cluster.global.mbarrier::complete_tx::bytes [%0], [%1], %2, [%3];\n}\n"
               ::"r"(dst), "l"(src), "r"(bytes), "r"(bar) : "memory");
}
__device__ __forceinline__ void e_prefetch(const void* p, int bytes) {
  asm volatile(ELECT "cp.async.bulk.prefetch.L2.global [%0], %1;\n}\n" ::"l"(p), "r"(bytes) : "memory");
}
__device__ __forceinline__ void e_store3d(const CUtensorMap* m, uint32_t src, int c1, int c2) {
  asm volatile(ELECT "cp.async.bulk.tensor.3d.global.shared::cta.bulk_group [%0, {%4,%2,%3}], [%1];\n"
               "@p cp.async.bulk.commit_group;\n@p cp.async.bulk.wait_group.read 0;\n}\n"
               ::"l"(m), "r"(src), "r"(c1), "r"(c2), "r"(0) : "memory");
}
__host__ __device__ constexpr uint64_t mkdesc(uint32_t addr, uint32_t lbo, uint32_t sbo, int swz) {
  return (uint64_t)((addr & 0x3FFFF) >> 4) | ((uint64_t)(lbo >> 4) << 16) | ((uint64_t)(sbo >> 4) << 32) |
         ((uint64_t)swz << 62);
}
#define WG_FENCE() asm volatile("wgmma.fence.sync.aligned;" ::: "memory")
#define WG_COMMIT() asm volatile("wgmma.commit_group.sync.aligned;" ::: "memory")
#define WG_WAIT(n) asm volatile("wgmma.wait_group.sync.aligned " #n ";" ::: "memory")

__device__ __forceinline__ void mma(float& d0, float& d1, float& d2, float& d3, uint32_t a0, uint32_t a1, uint32_t a2,
                                    uint32_t a3, uint32_t b0, uint32_t b1) {
  asm volatile("mma.sync.aligned.m16n8k16.row.col.f32.bf16.bf16.f32 {%0,%1,%2,%3},{%4,%5,%6,%7},{%8,%9},{%0,%1,%2,%3};"
               : "+f"(d0), "+f"(d1), "+f"(d2), "+f"(d3)
               : "r"(a0), "r"(a1), "r"(a2), "r"(a3), "r"(b0), "r"(b1));
}
__device__ __forceinline__ void mmac(float (&d)[4], uint32_t a0, uint32_t a1, uint32_t a2, uint32_t a3, uint32_t b0,
                                     uint32_t b1, const float (&c)[4]) {
  asm volatile("mma.sync.aligned.m16n8k16.row.col.f32.bf16.bf16.f32 {%0,%1,%2,%3},{%4,%5,%6,%7},{%8,%9},{%10,%11,%12,%13};"
               : "=f"(d[0]), "=f"(d[1]), "=f"(d[2]), "=f"(d[3])
               : "r"(a0), "r"(a1), "r"(a2), "r"(a3), "r"(b0), "r"(b1), "f"(c[0]), "f"(c[1]), "f"(c[2]), "f"(c[3]));
}
__device__ __forceinline__ void mma_p(int p, float (&d)[4], uint32_t a0, uint32_t a1, uint32_t a2, uint32_t a3, uint32_t b0, uint32_t b1) {
  asm volatile("{\n.reg .pred q;\nsetp.ne.b32 q, %10, 0;\n"
               "@q mma.sync.aligned.m16n8k16.row.col.f32.bf16.bf16.f32 {%0,%1,%2,%3},{%4,%5,%6,%7},{%8,%9},{%0,%1,%2,%3};\n}\n"
               : "+f"(d[0]), "+f"(d[1]), "+f"(d[2]), "+f"(d[3])
               : "r"(a0), "r"(a1), "r"(a2), "r"(a3), "r"(b0), "r"(b1), "r"(p));
}
__device__ __forceinline__ void mmac_p(int p, float (&d)[4], uint32_t a0, uint32_t a1, uint32_t a2, uint32_t a3, uint32_t b0,
                                       uint32_t b1, const float (&c)[4]) {
  asm volatile("{\n.reg .pred q;\nsetp.ne.b32 q, %14, 0;\n"
               "@q mma.sync.aligned.m16n8k16.row.col.f32.bf16.bf16.f32 {%0,%1,%2,%3},{%4,%5,%6,%7},{%8,%9},{%10,%11,%12,%13};\n}\n"
               : "+f"(d[0]), "+f"(d[1]), "+f"(d[2]), "+f"(d[3])
               : "r"(a0), "r"(a1), "r"(a2), "r"(a3), "r"(b0), "r"(b1), "f"(c[0]), "f"(c[1]), "f"(c[2]), "f"(c[3]), "r"(p));
}
__device__ __forceinline__ void mma_h(float (&d)[4], const uint32_t (&a)[4], uint32_t b0, uint32_t b1) {
  asm volatile("mma.sync.aligned.m16n8k16.row.col.f32.f16.f16.f32 {%0,%1,%2,%3},{%4,%5,%6,%7},{%8,%9},{%0,%1,%2,%3};"
               : "+f"(d[0]), "+f"(d[1]), "+f"(d[2]), "+f"(d[3]) : "r"(a[0]), "r"(a[1]), "r"(a[2]), "r"(a[3]), "r"(b0), "r"(b1));
}
__device__ __forceinline__ void mma_k8(float (&d)[4], uint32_t a0, uint32_t a1, uint32_t b0) {
  asm volatile("mma.sync.aligned.m16n8k8.row.col.f32.bf16.bf16.f32 {%0,%1,%2,%3},{%4,%5},{%6},{%0,%1,%2,%3};"
               : "+f"(d[0]), "+f"(d[1]), "+f"(d[2]), "+f"(d[3]) : "r"(a0), "r"(a1), "r"(b0));
}
__device__ __forceinline__ void mma0(float& d0, float& d1, float& d2, float& d3, uint32_t a0, uint32_t a1, uint32_t a2,
                                     uint32_t a3, uint32_t b0, uint32_t b1) {
  asm volatile("mma.sync.aligned.m16n8k16.row.col.f32.bf16.bf16.f32 {%0,%1,%2,%3},{%4,%5,%6,%7},{%8,%9},{%10,%10,%10,%10};"
               : "=f"(d0), "=f"(d1), "=f"(d2), "=f"(d3)
               : "r"(a0), "r"(a1), "r"(a2), "r"(a3), "r"(b0), "r"(b1), "f"(0.f));
}
__device__ __forceinline__ uint32_t pack_bf(float lo, float hi) {
  uint32_t r;
  asm("cvt.rn.bf16x2.f32 %0, %1, %2;" : "=r"(r) : "f"(hi), "f"(lo));
  return r;
}
__device__ __forceinline__ float bf_lo(uint32_t w) { return __uint_as_float(w << 16); }
__device__ __forceinline__ float bf_hi(uint32_t w) { return __uint_as_float(w & 0xffff0000u); }
__device__ __forceinline__ float bf_round(float x) { return __bfloat162float(__float2bfloat16_rn(x)); }
__device__ __forceinline__ uint32_t bmax2(uint32_t a, uint32_t b) {
  uint32_t r; asm("max.bf16x2 %0, %1, %2;" : "=r"(r) : "r"(a), "r"(b)); return r;
}
__device__ __forceinline__ uint32_t bmin2(uint32_t a, uint32_t b) {
  uint32_t r; asm("min.bf16x2 %0, %1, %2;" : "=r"(r) : "r"(a), "r"(b)); return r;
}
__device__ __forceinline__ float ex2(float x) { float r; asm("ex2.approx.ftz.f32 %0, %1;" : "=f"(r) : "f"(x)); return r; }
__device__ __forceinline__ float rcp(float x) { float r; asm("rcp.approx.ftz.f32 %0, %1;" : "=f"(r) : "f"(x)); return r; }
__device__ __forceinline__ void ldsm4(uint32_t (&r)[4], uint32_t a) {
  asm volatile("ldmatrix.sync.aligned.m8n8.x4.shared.b16 {%0,%1,%2,%3}, [%4];"
               : "=r"(r[0]), "=r"(r[1]), "=r"(r[2]), "=r"(r[3]) : "r"(a) : "memory");
}
__device__ __forceinline__ void ldsm4t(uint32_t (&r)[4], uint32_t a) {
  asm volatile("ldmatrix.sync.aligned.m8n8.x4.trans.shared.b16 {%0,%1,%2,%3}, [%4];"
               : "=r"(r[0]), "=r"(r[1]), "=r"(r[2]), "=r"(r[3]) : "r"(a) : "memory");
}
__device__ __forceinline__ void stsm4(uint32_t a, uint32_t r0, uint32_t r1, uint32_t r2, uint32_t r3) {
  asm volatile("stmatrix.sync.aligned.m8n8.x4.shared.b16 [%0], {%1,%2,%3,%4};"
               ::"r"(a), "r"(r0), "r"(r1), "r"(r2), "r"(r3) : "memory");
}
__device__ __forceinline__ uint32_t lds32(uint32_t a) {
  uint32_t r; asm volatile("ld.shared.u32 %0, [%1];" : "=r"(r) : "r"(a) : "memory"); return r;
}
__device__ __forceinline__ uint32_t lds16(uint32_t a) {
  uint32_t r; asm volatile("{\n.reg .u16 h;\nld.shared.u16 h, [%1];\ncvt.u32.u16 %0, h;\n}\n" : "=r"(r) : "r"(a) : "memory"); return r;
}
__device__ __forceinline__ uint2 lds64(uint32_t a) {
  uint2 r; asm volatile("ld.shared.v2.u32 {%0,%1}, [%2];" : "=r"(r.x), "=r"(r.y) : "r"(a) : "memory"); return r;
}
__device__ __forceinline__ uint4 lds128(uint32_t a) {
  uint4 r;
  asm volatile("ld.shared.v4.u32 {%0,%1,%2,%3}, [%4];" : "=r"(r.x), "=r"(r.y), "=r"(r.z), "=r"(r.w) : "r"(a) : "memory");
  return r;
}
__device__ __forceinline__ void sts32(uint32_t a, uint32_t v) { asm volatile("st.shared.u32 [%0], %1;" ::"r"(a), "r"(v) : "memory"); }
__device__ __forceinline__ void sts16(uint32_t a, uint32_t v) {
  asm volatile("{\n.reg .u16 h;\ncvt.u16.u32 h, %1;\nst.shared.u16 [%0], h;\n}\n" ::"r"(a), "r"(v) : "memory");
}
__device__ __forceinline__ void sts64(uint32_t a, uint32_t x, uint32_t y) {
  asm volatile("st.shared.v2.u32 [%0], {%1,%2};" ::"r"(a), "r"(x), "r"(y) : "memory");
}
__device__ __forceinline__ void sts128(uint32_t a, uint32_t x, uint32_t y, uint32_t z, uint32_t w) {
  asm volatile("st.shared.v4.u32 [%0], {%1,%2,%3,%4};" ::"r"(a), "r"(x), "r"(y), "r"(z), "r"(w) : "memory");
}
__device__ __forceinline__ uint4 ld_x(const uint4* p) {
  uint4 r;
  asm volatile("{\n.reg .b128 t;\nld.relaxed.gpu.global.b128 t, [%4];\nmov.b128 {%0,%1,%2,%3}, t;\n}\n"
               : "=r"(r.x), "=r"(r.y), "=r"(r.z), "=r"(r.w) : "l"(p) : "memory");
  return r;
}
__device__ __forceinline__ uint32_t ld_x32(const uint32_t* p) {
  uint32_t r; asm volatile("ld.relaxed.gpu.global.u32 %0, [%1];" : "=r"(r) : "l"(p) : "memory"); return r;
}
__device__ __forceinline__ void st_x(uint4* p, uint32_t x, uint32_t y, uint32_t z, uint32_t w) {
  asm volatile("{\n.reg .b128 t;\nmov.b128 t, {%1,%2,%3,%4};\nst.relaxed.gpu.global.b128 [%0], t;\n}\n"
               ::"l"(p), "r"(x), "r"(y), "r"(z), "r"(w) : "memory");
}
__device__ __forceinline__ void st_x_p(int p, uint4* a, uint32_t x, uint32_t y, uint32_t z, uint32_t w) {
  asm volatile("{\n.reg .b128 t;\n.reg .pred q;\nsetp.ne.b32 q, %5, 0;\nmov.b128 t, {%1,%2,%3,%4};\n@q st.relaxed.gpu.global.b128 [%0], t;\n}\n"
               ::"l"(a), "r"(x), "r"(y), "r"(z), "r"(w), "r"(p) : "memory");
}
__device__ __forceinline__ void sts64_p(int p, uint32_t a, uint32_t x, uint32_t y) {
  asm volatile("{\n.reg .pred q;\nsetp.ne.b32 q, %3, 0;\n@q st.shared.v2.u32 [%0], {%1,%2};\n}\n" ::"r"(a), "r"(x), "r"(y), "r"(p) : "memory");
}
__device__ __forceinline__ void st_x32(uint32_t* p, uint32_t x) {
  asm volatile("st.relaxed.gpu.global.u32 [%0], %1;" ::"l"(p), "r"(x) : "memory");
}
__device__ __forceinline__ uint32_t nz(uint32_t w) { return max(w, 1u); }
__device__ __forceinline__ uint32_t fu(float x) { return __float_as_uint(x); }
__device__ __forceinline__ float uf(uint32_t x) { return __uint_as_float(x); }

__device__ __forceinline__ void wgmma_ss_n96(float (&d)[48], uint64_t da, uint64_t db, int sc) {
  asm volatile("{\n.reg .pred p;\nsetp.ne.b32 p, %50, 0;\n"
      "wgmma.mma_async.sync.aligned.m64n96k16.f32.bf16.bf16 "
      "{%0,%1,%2,%3,%4,%5,%6,%7,%8,%9,%10,%11,%12,%13,%14,%15,%16,%17,%18,%19,%20,%21,%22,%23,%24,%25,%26,%27,%28,%29,%30,%31,%32,%33,%34,%35,%36,%37,%38,%39,%40,%41,%42,%43,%44,%45,%46,%47}, "
      "%48, %49, p, 1, 1, 0, 1;\n}\n"
      : "+f"(d[0]), "+f"(d[1]), "+f"(d[2]), "+f"(d[3]), "+f"(d[4]), "+f"(d[5]), "+f"(d[6]), "+f"(d[7]),
        "+f"(d[8]), "+f"(d[9]), "+f"(d[10]), "+f"(d[11]), "+f"(d[12]), "+f"(d[13]), "+f"(d[14]), "+f"(d[15]),
        "+f"(d[16]), "+f"(d[17]), "+f"(d[18]), "+f"(d[19]), "+f"(d[20]), "+f"(d[21]), "+f"(d[22]), "+f"(d[23]),
        "+f"(d[24]), "+f"(d[25]), "+f"(d[26]), "+f"(d[27]), "+f"(d[28]), "+f"(d[29]), "+f"(d[30]), "+f"(d[31]),
        "+f"(d[32]), "+f"(d[33]), "+f"(d[34]), "+f"(d[35]), "+f"(d[36]), "+f"(d[37]), "+f"(d[38]), "+f"(d[39]),
        "+f"(d[40]), "+f"(d[41]), "+f"(d[42]), "+f"(d[43]), "+f"(d[44]), "+f"(d[45]), "+f"(d[46]), "+f"(d[47])
      : "l"(da), "l"(db), "r"(sc));
}

__device__ __forceinline__ void wgmma_ss_n128(float (&d)[64], uint64_t da, uint64_t db, int sc) {
  asm volatile("{\n.reg .pred p;\nsetp.ne.b32 p, %66, 0;\n"
      "wgmma.mma_async.sync.aligned.m64n128k16.f32.bf16.bf16 "
      "{%0,%1,%2,%3,%4,%5,%6,%7,%8,%9,%10,%11,%12,%13,%14,%15,%16,%17,%18,%19,%20,%21,%22,%23,%24,%25,%26,%27,%28,%29,%30,%31,%32,%33,%34,%35,%36,%37,%38,%39,%40,%41,%42,%43,%44,%45,%46,%47,%48,%49,%50,%51,%52,%53,%54,%55,%56,%57,%58,%59,%60,%61,%62,%63}, "
      "%64, %65, p, 1, 1, 0, 1;\n}\n"
      : "+f"(d[0]), "+f"(d[1]), "+f"(d[2]), "+f"(d[3]), "+f"(d[4]), "+f"(d[5]), "+f"(d[6]), "+f"(d[7]),
        "+f"(d[8]), "+f"(d[9]), "+f"(d[10]), "+f"(d[11]), "+f"(d[12]), "+f"(d[13]), "+f"(d[14]), "+f"(d[15]),
        "+f"(d[16]), "+f"(d[17]), "+f"(d[18]), "+f"(d[19]), "+f"(d[20]), "+f"(d[21]), "+f"(d[22]), "+f"(d[23]),
        "+f"(d[24]), "+f"(d[25]), "+f"(d[26]), "+f"(d[27]), "+f"(d[28]), "+f"(d[29]), "+f"(d[30]), "+f"(d[31]),
        "+f"(d[32]), "+f"(d[33]), "+f"(d[34]), "+f"(d[35]), "+f"(d[36]), "+f"(d[37]), "+f"(d[38]), "+f"(d[39]),
        "+f"(d[40]), "+f"(d[41]), "+f"(d[42]), "+f"(d[43]), "+f"(d[44]), "+f"(d[45]), "+f"(d[46]), "+f"(d[47]),
        "+f"(d[48]), "+f"(d[49]), "+f"(d[50]), "+f"(d[51]), "+f"(d[52]), "+f"(d[53]), "+f"(d[54]), "+f"(d[55]),
        "+f"(d[56]), "+f"(d[57]), "+f"(d[58]), "+f"(d[59]), "+f"(d[60]), "+f"(d[61]), "+f"(d[62]), "+f"(d[63])
      : "l"(da), "l"(db), "r"(sc));
}

__device__ __forceinline__ void wgmma_rs_n16(float (&d)[8], const uint4& a, uint64_t db, int sc) {
  asm volatile("{\n.reg .pred p;\nsetp.ne.b32 p, %13, 0;\n"
      "wgmma.mma_async.sync.aligned.m64n16k16.f32.bf16.bf16 "
      "{%0,%1,%2,%3,%4,%5,%6,%7}, "
      "{%8,%9,%10,%11}, %12, p, 1, 1, 1;\n}\n"
      : "+f"(d[0]), "+f"(d[1]), "+f"(d[2]), "+f"(d[3]), "+f"(d[4]), "+f"(d[5]), "+f"(d[6]), "+f"(d[7])
      : "r"(a.x), "r"(a.y), "r"(a.z), "r"(a.w), "l"(db), "r"(sc));
}

struct Params {
  const __nv_bfloat16 *logA, *Aim, *Cre, *Cim, *logdt, *Dskip, *x, *wphi, *wo;
  __nv_bfloat16* out;
  uint4* xs;
  long long* ts;
};

__device__ __forceinline__ uint4 tr_row(const uint4 (&v)[8], int i) {
  uint32_t o[4];
#pragma unroll
  for (int m = 0; m < 4; m++) {
    const uint4 &ra = v[2 * m], &rb = v[2 * m + 1];
    const int k = i >> 1;
    const uint32_t xa = k == 0 ? ra.x : k == 1 ? ra.y : k == 2 ? ra.z : ra.w;
    const uint32_t xb = k == 0 ? rb.x : k == 1 ? rb.y : k == 2 ? rb.z : rb.w;
    o[m] = __byte_perm(xa, xb, (i & 1) ? 0x7632 : 0x5410);
  }
  return make_uint4(o[0], o[1], o[2], o[3]);
}

struct cpx { float r, i; };
__device__ __forceinline__ cpx csq(cpx a) { return {a.r * a.r - a.i * a.i, 2.f * (a.r * a.i)}; }
__device__ __forceinline__ cpx polar(float e, float t) {
  const float m = ex2(e);
  return {m * __cosf(t), m * __sinf(t)};
}

struct KgenRaw { unsigned short la, ai, cr, ci, ldt; };
__device__ __forceinline__ KgenRaw kgen_load(const Params& P, int d, int unit, int lane) {
  const int o = d * 128 + unit * 32 + lane;
  return {__ldg((const unsigned short*)P.logA + o), __ldg((const unsigned short*)P.Aim + o), __ldg((const unsigned short*)P.Cre + o),
          __ldg((const unsigned short*)P.Cim + o), __ldg((const unsigned short*)P.logdt + d)};
}
struct hmul { __half2 a, b; };
__device__ __forceinline__ hmul mk_mul(cpx w) {
  uint32_t b;
  asm("{\n.reg .f32 n;\nneg.ftz.f32 n, %1;\ncvt.rn.f16x2.f32 %0, %2, n;\n}\n" : "=r"(b) : "f"(w.i), "f"(w.r));
  return {__floats2half2_rn(w.r, w.i), *(const __half2*)&b};
}
__device__ __forceinline__ __half2 hcm(__half2 z, const hmul& w) { return __hfma2(__high2half2(z), w.b, __hmul2(__low2half2(z), w.a)); }
__device__ __forceinline__ uint32_t hu(__half2 v) { return *(const uint32_t*)&v; }

struct KgenAddr { uint32_t sa, sb, lb, lc, la; };
__device__ __forceinline__ KgenAddr kgen_addr(int lane, uint32_t buf) {
  KgenAddr a;
  a.sa = buf + (lane & 7) * 128 + ((((lane >> 3) ^ lane) & 7) << 4);
  a.lb = buf + (lane >> 3) * 128 + (((lane ^ (lane >> 3)) & 7) << 4);
  a.la = buf + ((lane >> 3) & 1) * 1024 + (lane >> 4) * 128 + (((lane ^ (lane >> 4)) & 7) << 4);
  a.sb = a.sa ^ 64; a.lc = a.lb ^ 64;
  asm volatile("" : "+r"(a.sa), "+r"(a.sb), "+r"(a.lb), "+r"(a.lc), "+r"(a.la));
  return a;
}
__device__ __forceinline__ void kgen_unit(const KgenRaw& r, const KgenAddr& ad, uint32_t zero, float (&k)[5][4], float& k2048, float& sc) {
  const float dt = bf_round(expf(bf_lo(r.ldt)));
  const float a2 = bf_round(ex2(bf_lo(r.la) * 1.4426950408889634f)) * (dt * -1.4426950408889634f);
  const float f = bf_lo(r.ai) * dt;
  const float r128 = f * 20.371832715762604f;
  const uint32_t ex = min(max(__reduce_max_sync(0xffffffffu, max(r.cr & 0x7fffu, r.ci & 0x7fffu)) >> 7, 1u), 253u);
  const float cs = uf((254u - ex) << 23);
  sc = 2.f * dt * uf(ex << 23);
  const cpx C = {bf_lo(r.cr) * cs, -bf_lo(r.ci) * cs};
  auto put = [&](const __half2 (&v)[8], uint32_t off) {
    stsm4(ad.sa + off, hu(v[0]), hu(v[1]), hu(v[2]), hu(v[3]));
    stsm4(ad.sb + off, hu(v[4]), hu(v[5]), hu(v[6]), hu(v[7]));
  };
  uint32_t A[4][4], B[5][2][4];
  auto get = [&](int j, uint32_t off) {
    __syncwarp();
    ldsm4(B[j][0], ad.lb + off);
    ldsm4(B[j][1], ad.lc + 512 + off);
  };
  auto tile = [&](int j) {
    k[j][0] = k[j][1] = k[j][2] = k[j][3] = 0.f;
#pragma unroll
    for (int s = 0; s < 4; s++) mma_h(k[j], A[s], B[j][s >> 1][2 * (s & 1)], B[j][s >> 1][2 * (s & 1) + 1]);
  };
  auto after = [&](cpx v, uint32_t dep) { return cpx{uf(fu(v.r) ^ (dep & zero)), v.i}; };
  const cpx w1 = polar(a2, f), w128 = polar(a2 * 128.f, (r128 - rintf(r128)) * 6.283185307179586f);
  const cpx w2 = csq(w1), w4 = csq(w2);
  __half2 t0[8], t1[8], t2[8], t3[8], t4[8];
  const hmul m2 = mk_mul(w2), m4 = mk_mul(w4), m128 = mk_mul(w128);
  t0[0] = __floats2half2_rn(1.f, 0.f); t0[1] = __floats2half2_rn(w1.r, w1.i); t0[2] = m2.a; t0[4] = m4.a;
  t0[3] = hcm(t0[1], m2); t0[5] = hcm(t0[1], m4); t0[6] = hcm(t0[2], m4); t0[7] = hcm(t0[3], m4);
  put(t0, 0); get(0, 0);
  t1[0] = m128.a;
#pragma unroll
  for (int i = 1; i < 8; i++) t1[i] = hcm(t0[i], m128);
  put(t1, 1024); get(1, 1024);
  {
    cpx w8 = csq(after(w4, B[0][0][0]));
    w8.i = -w8.i;
    const cpx w16 = csq(w8), w32 = csq(w16), w64 = csq(w32);
    const hmul m8 = mk_mul(w8), m16 = mk_mul(w16), m32 = mk_mul(w32), m64 = mk_mul(w64);
    __half2 a[8];
    a[0] = __floats2half2_rn(C.r, C.i); a[1] = hcm(a[0], m8);
    a[2] = hcm(a[0], m16); a[3] = hcm(a[1], m16);
#pragma unroll
    for (int i = 0; i < 4; i++) a[4 + i] = hcm(a[i], m32);
    put(a, 0);
#pragma unroll
    for (int i = 0; i < 8; i++) a[i] = hcm(a[i], m64);
    put(a, 1024);
    __syncwarp();
#pragma unroll
    for (int s = 0; s < 4; s++) ldsm4(A[s], (ad.la ^ (s << 5)) + s * 256);
  }
  const cpx w256 = csq(after(w128, B[1][0][0]));
  const hmul m256 = mk_mul(w256);
  t2[0] = m256.a;
#pragma unroll
  for (int i = 1; i < 8; i++) t2[i] = hcm((i & 1) ? t1[i & 6] : t0[i & 6], m256);
  put(t2, 0); get(2, 0);
  tile(0); tile(1);
  const cpx w512 = csq(after(w256, A[0][0]));
  const hmul m512 = mk_mul(w512);
  t3[0] = m512.a;
#pragma unroll
  for (int i = 1; i < 8; i++) t3[i] = hcm((i & 2) ? t2[i & 5] : ((i & 1) ? t1[i & 4] : t0[i & 4]), m512);
  put(t3, 1024); get(3, 1024);
  tile(2);
  const cpx w1024 = csq(after(w512, B[2][0][0])), we = csq(w1024);
  const hmul m1024 = mk_mul(w1024);
  t4[0] = m1024.a;
#pragma unroll
  for (int i = 1; i < 8; i++) t4[i] = hcm((i & 4) ? t3[i & 3] : ((i & 2) ? t2[i & 1] : t1[0]), m1024);
  put(t4, 0); get(4, 0);
  tile(3); tile(4);
  k2048 = (C.r * we.r + C.i * we.i) * sc;
}

__device__ __forceinline__ void build_tables(uint32_t tb, int lane, float (&k)[5][4], float k2048) {
  const int g = lane >> 2, c = lane & 3;
  const uint32_t kc = tb + T_KC + 16;
  {
    const uint32_t a0 = kc + 16 * g + 4 * c, a2 = kc + 2 * (256 + 4 * g + c);
    const uint32_t a3 = kc + 2 * (384 + 2 * g + 64 * (c & 1) + (c >> 1)), a4 = kc + 2 * (512 + g + 32 * c);
#pragma unroll
    for (int r = 0; r < 2; r++) {
      sts32(a0 + 128 * r, pack_bf(k[0][2 * r], k[0][2 * r + 1]));
      sts32(a0 + 128 * r + 256, pack_bf(k[1][2 * r], k[1][2 * r + 1]));
      const uint32_t w2 = pack_bf(k[2][2 * r], k[2][2 * r + 1]);
      const uint32_t w3 = pack_bf(k[3][2 * r], k[3][2 * r + 1]);
      const uint32_t w4 = pack_bf(k[4][2 * r], k[4][2 * r + 1]);
      sts16(a2 + 64 * r, w2); sts16(a2 + 64 * r + 128, w2 >> 16);
      sts16(a3 + 32 * r, w3); sts16(a3 + 32 * r + 64, w3 >> 16);
      sts16(a4 + 16 * r, w4); sts16(a4 + 16 * r + 32, w4 >> 16);
    }
  }
  if (lane == 0) { sts16(kc + 2 * 640, pack_bf(k2048, 0.f)); sts16(kc - 2, 0); }
  __syncwarp();
  const uint32_t td = tb + T_D + 32;
  {
    const uint4 v = lds128(kc + 16 * lane);
    const uint32_t pv = lds16(kc + 16 * lane - 2);
    sts128(td + 32 * lane, __byte_perm(v.x, pv, 0x5410), __byte_perm(v.x, v.x, 0x1032), __byte_perm(v.y, v.x, 0x7610),
           __byte_perm(v.y, v.y, 0x1032));
    sts128(td + 32 * lane + 16, __byte_perm(v.z, v.y, 0x7610), __byte_perm(v.z, v.z, 0x1032),
           __byte_perm(v.w, v.z, 0x7610), __byte_perm(v.w, v.w, 0x1032));
  }
  {
    const uint2 v = lds64(kc + 512 + 8 * lane);
    const uint32_t k4 = lds16(kc + 512 + 8 * lane + 8);
    const uint32_t pv = lds16(kc + (lane == 0 ? 510 : 512 + 8 * lane));
    const uint32_t k22 = __byte_perm(v.y, v.y, 0x1010);
    sts128(td + 1024 + 32 * lane, __byte_perm(v.x, pv, 0x5410), __byte_perm(v.x, v.x, 0x1010),
           __byte_perm(v.x, v.x, 0x1032), __byte_perm(v.y, v.x, 0x7610));
    sts128(td + 1024 + 32 * lane + 16, k22, k22, __byte_perm(v.y, v.y, 0x1032), __byte_perm(k4, v.y, 0x7610));
  }
  {
    const uint32_t kk = lds16(kc + 2 * 384);
    const uint32_t w = lane < 3 ? (kk | (kk << 16)) : (lane == 3 ? (kk << 16) : 0u);
    if (lane < 24) sts32(td + 4 * (lane < 16 ? 512 + lane : lane - 24), w);
    const uint32_t lo_ = lds16(kc + 2 * 511), le_ = lds16(kc + 2 * 512);
    const uint32_t ja = tb + T_5 + (lane < 16 ? 4 * lane : 256 + 4 * lane);
    sts32(ja, lane == 16 ? (le_ << 16) : 0u);
    sts32(ja + 384, lane == 16 ? (lo_ << 16) : 0u);
    sts32(tb + (lane < 16 ? T_7 : T_9 - 64) + 4 * lane, 0u);
  }
#pragma unroll
  for (int s = 0; s < 2; s++) {
    const uint32_t b = kc + 2 * (s ? 512 : 384) + 8 * lane;
    const uint2 v = lds64(b);
    uint32_t em = lds16(b - 2), e0 = v.x;
    const uint32_t e4 = lds16(b + 8);
    if (lane == 0) { em = 0; e0 = 0; }
    sts64(tb + (s ? T_7 : T_3) + 64 + 8 * lane, __byte_perm(v.x, em, 0x5432), __byte_perm(v.y, v.x, 0x7632));
    sts64(tb + (s ? T_9 : T_5) + 64 + 8 * lane, __byte_perm(v.y, e0, 0x5410), __byte_perm(e4, v.y, 0x5410));
  }
  __syncwarp();
}

__device__ __forceinline__ uint32_t box2w(int lo, int n, int o) {
  return ((unsigned)(o - lo) < (unsigned)n ? 0x3F80u : 0u) | ((unsigned)(o + 1 - lo) < (unsigned)n ? 0x3F800000u : 0u);
}

#define SPLIT() asm volatile("{\n.reg .pred p;\nsetp.ne.u32 p, %0, 0;\n@p exit;\n}\n" ::"r"(blockIdx.y) : "memory")

__device__ __forceinline__ void conv_channel(uint32_t ub, uint32_t tb, int lane, uint4* ydst) {
  const int g = lane >> 2, c = lane & 3, x = g - 2 * c;
  const int mi = lane >> 3;
  const uint32_t qa = ub + U_PAD + 16 * (lane & 7) + ((mi == 0 || mi == 3) ? U_ODD : 0) - (mi == 0 ? 16 : 0);
  const uint32_t hb = ub + U_PAD + (mi & 1) * U_ODD + 16 * ((lane >> 4) + (lane & 7)) - 16;
  const uint32_t kv = lds16(tb + T_KC + 16 + 2 * 512);
  const int oh = c < 2 ? 8 + 2 * c : 2 * c - 8, og = c < 3 ? 2 * c : -10;
  uint32_t bx[4] = {box2w(g - 4, 9, 2 * c), box2w(g - 3, 7, 2 * c), box2w(g - 4, 9, oh), box2w(g - 3, 7, oh)};
  uint32_t by[4] = {box2w(g - 10, 5, 2 * c - 8), box2w(g - 5, 3, 2 * c - 8), box2w(g - 10, 5, og), box2w(g - 5, 3, og)};
  uint32_t lb0 = ((unsigned)(x + 5) < 2u ? kv : 0u) | ((unsigned)(x + 4) < 2u ? kv << 16 : 0u);
  uint32_t lb1 = ((unsigned)(x - 3) < 2u ? kv : 0u) | ((unsigned)(x - 4) < 2u ? kv << 16 : 0u);
  const int q0 = g - 1, q1 = c < 3 ? g : g - 2;
  uint32_t y0a = ub + U_PAD + (q0 & 1) * U_ODD + 16 * (q0 >> 1) + 4 * c;
  uint32_t y1a = ub + U_PAD + (q1 & 1) * U_ODD + 16 * (q1 >> 1) + 4 * c;
  uint32_t f3[3][4][4];
  {
    const uint32_t fa = tb + T_7 + 4 * (16 + x);
#pragma unroll
    for (int tt = 0; tt < 3; tt++)
#pragma unroll
      for (int D = 0; D < 4; D++) {
        const uint32_t a = fa + (tt == 0 ? 316 : (tt == 1 ? 320 : 0)) + 64 * D;
        f3[tt][D][0] = lds32(a); f3[tt][D][1] = lds32(a + 32); f3[tt][D][2] = lds32(a - 32); f3[tt][D][3] = lds32(a);
      }
  }
#pragma unroll
  for (int i = 0; i < 4; i++) asm volatile("" : "+r"(bx[i]), "+r"(by[i]));
  asm volatile("" : "+r"(lb0), "+r"(lb1), "+r"(y0a), "+r"(y1a));
  mbar_wait(BAR(MB_UFULL));
  mbar_wait(BAR(MB_EMPTY + 15));
  TS(36);
  float acc[16][4];
  {
    uint32_t z09[8], z07[8], zm9[8], zm7[8];
#pragma unroll
    for (int i = 0; i < 8; i++) {
      uint32_t h[4];
      ldsm4(h, hb + 128 * i);
      float y0, y1, y2, y3, w0, w1, w2, w3;
      mma0(y0, y1, y2, y3, bx[0], bx[1], bx[2], bx[3], h[2], c < 2 ? h[3] : h[1]);
      mma0(w0, w1, w2, w3, bx[0], bx[1], bx[2], bx[3], h[1], c < 2 ? h[2] : h[0]);
      z09[i] = pack_bf(y0, y1); z07[i] = pack_bf(y2, y3);
      zm9[i] = pack_bf(w0, w1); zm7[i] = pack_bf(w2, w3);
    }
    float a[4][2][4];
#pragma unroll
    for (int kap = 0; kap < 4; kap++)
#pragma unroll
      for (int sg = 0; sg < 2; sg++)
#pragma unroll
        for (int bk = 3; bk >= kap; bk--) {
          const uint32_t(&q0_)[4] = f3[sg ? 2 : 0][bk - kap];
          const uint32_t(&q1_)[4] = f3[sg ? 2 : 1][bk - kap];
          float(&a0)[4] = a[bk][0];
          float(&a1)[4] = a[bk][1];
          if (sg == 0 && kap == 0) {
            mma0(a0[0], a0[1], a0[2], a0[3], q0_[0], q0_[1], q0_[2], q0_[3], z09[0], z09[1]);
            mma0(a1[0], a1[1], a1[2], a1[3], q1_[0], q1_[1], q1_[2], q1_[3], zm9[0], zm9[1]);
          } else {
            mma(a0[0], a0[1], a0[2], a0[3], q0_[0], q0_[1], q0_[2], q0_[3], sg ? zm7[2 * kap] : z09[2 * kap], sg ? zm7[2 * kap + 1] : z09[2 * kap + 1]);
            mma(a1[0], a1[1], a1[2], a1[3], q1_[0], q1_[1], q1_[2], q1_[3], sg ? z07[2 * kap] : zm9[2 * kap], sg ? z07[2 * kap + 1] : zm9[2 * kap + 1]);
          }
        }
    SPLIT();
#pragma unroll
    for (int i = 0; i < 8; i++) {
      uint32_t h[4];
      ldsm4(h, qa + 128 * i);
      const float ci[4] = {a[i >> 1][0][2 * (i & 1)], a[i >> 1][0][2 * (i & 1) + 1], a[i >> 1][1][2 * (i & 1)], a[i >> 1][1][2 * (i & 1) + 1]};
      mmac(acc[8 + i], h[0], h[1], h[2], h[3], lb0, lb1, ci);
    }
  }
  TS(44);
  {
    uint2 a5[10], a3[10];
    const uint32_t aa = tb + T_5 + 4 * (8 + 2 * g - 2 * c);
#pragma unroll
    for (int m = 0; m < 10; m++) { a5[m] = lds64(aa + 32 * m); a3[m] = lds64(aa + 384 + 32 * m); }
    uint32_t x5[12][2], x3[12][2];
    auto ygen = [&](int kap) {
#pragma unroll
      for (int hh = 0; hh < 2; hh++) {
        float y0, y1, y2, y3;
        mma0(y0, y1, y2, y3, by[0], by[1], by[2], by[3], lds32(y0a + 128 * kap + 64 * hh), lds32(y1a + 128 * kap + 64 * hh));
        x5[kap][hh] = pack_bf(y0, y1);
        x3[kap][hh] = pack_bf(y2, y3);
      }
    };
    ygen(11); ygen(10); ygen(9); ygen(8);
#pragma unroll
    for (int kap = 11; kap >= 0; kap--) {
      if (kap >= 4) ygen(kap - 4);
#pragma unroll
      for (int sg = 0; sg < 2; sg++)
#pragma unroll
        for (int i = 4; i >= 0; i--) {
          const int be = kap + 4 + i;
          if (be <= 15) {
            const uint2 &hi = sg ? a3[2 * i + 1] : a5[2 * i + 1], &lo = sg ? a3[2 * i] : a5[2 * i];
            const uint32_t b0 = sg ? x3[kap][0] : x5[kap][0], b1 = sg ? x3[kap][1] : x5[kap][1];
            if (be < 8 && i == 0 && sg == 0) mma0(acc[be][0], acc[be][1], acc[be][2], acc[be][3], hi.x, hi.y, lo.x, lo.y, b0, b1);
            else mma(acc[be][0], acc[be][1], acc[be][2], acc[be][3], hi.x, hi.y, lo.x, lo.y, b0, b1);
          }
        }
    }
  }
  TS(45);
  {
    const uint32_t st = tb + T_ST + lane * 8;
#pragma unroll
    for (int be = 4; be < 12; be++) sts64(st + 256 * be, pack_bf(acc[be][0], acc[be][1]), pack_bf(acc[be][2], acc[be][3]));
    SPLIT();
    uint32_t F[66], qd[8][4];
    const uint32_t fa = tb + T_D + 32 + 4 * x;
#pragma unroll
    for (int i = 0; i < 32; i++) {
      const int s = 120 - (i >> 2) - 8 * (i & 3);
      uint32_t(&q)[4] = qd[i & 7];
      ldsm4(q, qa + 16 * s);
      const int m = 16 * (i & 3) + 2 * (i >> 2);
      F[m] = lds32(fa + 32 * m); F[m + 1] = lds32(fa + 32 * m + 32);
#pragma unroll
      for (int be = 15; be >= 12; be--) {
        const int de = 8 * be - s;
        if (de >= 0) mma(acc[be][0], acc[be][1], acc[be][2], acc[be][3], q[0], q[1], q[2], q[3], F[2 * de + 1], F[2 * de]);
      }
    }
    F[64] = lds32(fa + 32 * 64); F[65] = lds32(fa + 32 * 65);
    uint32_t qp = qa + 128 * 11, sta = st + 256 * 10;
    uint4* yd = ydst + 7 * 32;
#pragma unroll
    for (int i = 0; i < 6; i++) ldsm4(qd[i], qp - 16 * i);
    uint2 sv = lds64(sta + 256);
    float ci[4] = {bf_lo(sv.x), bf_hi(sv.x), bf_lo(sv.y), bf_hi(sv.y)};
    float T[5][4];
#pragma unroll
    for (int i = 0; i < 16; i++) T[i >> 2][i & 3] = acc[12 + (i >> 2)][i & 3];
    nb_sync(NB_YZ, 160);
    TS(46);
#pragma unroll 1
    for (int bp = 5; bp >= 0; bp--) {
      uint32_t held[2];
#pragma unroll
      for (int o = 1; o >= 0; o--) {
#pragma unroll
        for (int k = 4; k >= 1; k--) mmac(T[k], qd[0][0], qd[0][1], qd[0][2], qd[0][3], F[16 * k + 1], F[16 * k], T[k - 1]);
        mmac(T[0], qd[0][0], qd[0][1], qd[0][2], qd[0][3], F[1], F[0], ci);
        ldsm4(qd[6], qp - 16 * 6);
        ldsm4(qd[7], qp - 16 * 7);
        sv = lds64(sta);
#pragma unroll
        for (int i = 1; i < 8; i++) {
#pragma unroll
          for (int k = 3; k >= 0; k--)
            mma(T[k][0], T[k][1], T[k][2], T[k][3], qd[i][0], qd[i][1], qd[i][2], qd[i][3], F[16 * k + 2 * i + 1], F[16 * k + 2 * i]);
          if (i < 7) ldsm4(qd[i - 1], qp - 128 - 16 * (i - 1));
          if (i == 2) {
            const uint32_t w0 = pack_bf(T[4][0], T[4][1]), w1 = pack_bf(T[4][2], T[4][3]);
            if (o) { held[0] = w0; held[1] = w1; }
            else st_x(yd, nz(w0), w1, held[0], held[1]);
          }
          if (i == 4) {
            if (2 * bp + o <= 4) sv = make_uint2(0, 0);
            ci[0] = bf_lo(sv.x); ci[1] = bf_hi(sv.x); ci[2] = bf_lo(sv.y); ci[3] = bf_hi(sv.y);
          }
        }
        qp -= 128; sta -= 256;
      }
      yd -= 32;
    }
#pragma unroll
    for (int B = 1; B >= 0; B--)
      st_x(ydst + B * 32, nz(pack_bf(T[2 * B][0], T[2 * B][1])), pack_bf(T[2 * B][2], T[2 * B][3]),
           pack_bf(T[2 * B + 1][0], T[2 * B + 1][1]), pack_bf(T[2 * B + 1][2], T[2 * B + 1][3]));
  }
}

__device__ __forceinline__ void dual_exp(const uint32_t* w, uint32_t* e) {
  const float L = 1.44268798828125f;
  uint32_t mx = bmax2(bmax2(w[0], w[1]), bmax2(w[2], w[3]));
  uint32_t mn = bmin2(bmin2(w[0], w[1]), bmin2(w[2], w[3]));
  mx = bmax2(mx, __shfl_xor_sync(0xffffffffu, mx, 1));
  mn = bmin2(mn, __shfl_xor_sync(0xffffffffu, mn, 1));
  mx = bmax2(mx, __shfl_xor_sync(0xffffffffu, mx, 2));
  mn = bmin2(mn, __shfl_xor_sync(0xffffffffu, mn, 2));
  const float mx0 = bf_lo(mx) * -L, mx1 = bf_hi(mx) * -L, mn0 = bf_lo(mn) * L, mn1 = bf_hi(mn) * L;
#pragma unroll
  for (int i = 0; i < 2; i++) {
    const float a0 = bf_lo(w[2 * i]), a1 = bf_hi(w[2 * i]), b0 = bf_lo(w[2 * i + 1]), b1 = bf_hi(w[2 * i + 1]);
    e[2 * i] = pack_bf(ex2(fmaf(a0, L, mx0)), ex2(fmaf(b0, L, mx0)));
    e[2 * i + 1] = pack_bf(ex2(fmaf(a1, L, mx1)), ex2(fmaf(b1, L, mx1)));
    e[4 + 2 * i] = pack_bf(ex2(fmaf(a0, -L, mn0)), ex2(fmaf(b0, -L, mn0)));
    e[5 + 2 * i] = pack_bf(ex2(fmaf(a1, -L, mn1)), ex2(fmaf(b1, -L, mn1)));
  }
}
__device__ __forceinline__ void norm_store(const uint32_t* e, uint32_t dst) {
  float s[4];
  mma0(s[0], s[1], s[2], s[3], e[0], e[1], e[2], e[3], 0x3F803F80u, 0x3F803F80u);
  const uint32_t r = pack_bf(rcp(s[0]), rcp(s[2]));
  const __nv_bfloat162 rr = *(const __nv_bfloat162*)&r;
  uint32_t o[4];
#pragma unroll
  for (int i = 0; i < 4; i++) {
    const __nv_bfloat162 v = __hmul2(*(const __nv_bfloat162*)&e[i], (i & 1) ? __high2bfloat162(rr) : __low2bfloat162(rr));
    o[i] = *(const uint32_t*)&v;
  }
  stsm4(dst, o[0], o[1], o[2], o[3]);
}

__global__ void __launch_bounds__(NTHREADS, 1)
fused_kernel(const Params P, const __grid_constant__ CUtensorMap mx, const __grid_constant__ CUtensorMap mw,
             const __grid_constant__ CUtensorMap mo, const __grid_constant__ CUtensorMap mu,
             const __grid_constant__ CUtensorMap mout, const __grid_constant__ CUtensorMap mw4) {
  constexpr uint32_t sb = SB;
  const int tid = threadIdx.x, lane = tid & 31;
  const int warp = __shfl_sync(0xffffffffu, tid >> 5, 0);
  const int b = blockIdx.x, oct = b >> 3, i8 = b & 7;
  const int rt = oct < 8 ? oct : 15 - oct;
  const int hp = (oct >> 3) * 8 + i8;

  const int wg = warp >> 2, w = warp & 3;
  const int d = b * 4 + ((tid >> 5) & 3);
  if (tid < 384) {
    asm volatile("prefetch.tensormap [%0];" ::"l"(&mu) : "memory");
    asm volatile("prefetch.tensormap [%0];" ::"l"(&mw) : "memory");
    asm volatile("prefetch.tensormap [%0];" ::"l"(&mx) : "memory");
    asm volatile("prefetch.tensormap [%0];" ::"l"(&mw4) : "memory");
  }
  if (warp == 12) {
    if (lane == 0) {
#pragma unroll
      for (int i = 0; i < 9; i++) mbar_init(BAR(i), 1);
      asm volatile("fence.mbarrier_init.release.cluster;" ::: "memory");
    }
    __syncwarp();
    if (lane < 9) mbar_expect(BAR(0) + 8 * lane, lane == 5 ? 65536 : ((lane == 0 || lane > 5) ? 16384 : 28672));
    __syncwarp();
    e_tma3d(sb + OFF_W, &mw, BAR(MB_FULL), hp * 32, 0, 0);
    e_tma2d(sb + OFF_X + 3 * 16384, &mx, BAR(MB_FULL), 0, rt * 256);
  } else if (warp == 13) {
    if (lane == 0) {
#pragma unroll
      for (int i = 9; i < 39; i++) mbar_init(BAR(i), i < MB_EMPTY ? 1 : (i < MB_AUX ? 4 : 5));
      asm volatile("fence.mbarrier_init.release.cluster;" ::: "memory");
    }
    __syncwarp();
    if (lane < 9) mbar_expect(BAR(MB_FULL + 8) + 8 * lane, lane < 8 ? 16384 : 131072);
  }
  const KgenRaw raw = kgen_load(P, d, tid >> 7, lane);
  const unsigned short dsk = __ldg((const unsigned short*)P.Dskip + d);
  const uint32_t tb = sb + OFF_T + w * T_CH;
  const uint32_t kp = wg == 3 ? sb + OFF_X + 32768 + w * 4096 : tb + (wg & 1) * 2608;
  const KgenAddr kad = kgen_addr(lane, wg == 2 ? sb + OFF_STG0 + 16384 + w * 2048 : (kp + 127) & ~127u);
  if (warp == 12) {
#pragma unroll 1
    for (int kb = 1; kb < 4; kb++) {
      if (kb == U_AT) e_tma5d(sb + OFF_STG0, &mu, BAR(MB_URAW), i8 * 64, oct * 4);
      e_tma3d(sb + OFF_W + kb * 12288, &mw, BAR(MB_FULL) + 8 * kb, hp * 32, kb * 64, 0);
      e_tma2d(sb + OFF_X + (kb < 2 ? kb + 3 : kb - 2) * 16384, &mx, BAR(MB_FULL) + 8 * kb, kb * 64, rt * 256);
    }
    e_prefetch(P.x + (size_t)(rt * 256 + hp * 16) * 512, 16384);
    e_tma4d(sb + OFF_W + 4 * 12288, &mw4, BAR(MB_FULL + 4), hp * 32, 4);
    if (smem_u32(smem_raw) != SB) __trap();
    if (lane == 0) TS1(54);
  }
  float k[5][4], k2048, ksc;
  kgen_unit(raw, kad, blockIdx.y, k, k2048, ksc);
  TS(40 + wg);
  if ((fu(k[0][0]) & fu(k[1][0]) & fu(k[2][0]) & fu(k[3][0]) & fu(k[4][0])) == 0xffffffffu) sts32(kp, 0);
  if (wg) nb_arrive(0, 512);
  k2048 += __shfl_xor_sync(0xffffffffu, k2048, 16);
  k2048 += __shfl_xor_sync(0xffffffffu, k2048, 8);
  if (wg != 2) {
#pragma unroll
    for (int j = 0; j < 5; j++) sts128(kp + j * 512 + lane * 16, fu(k[j][0]), fu(k[j][1]), fu(k[j][2]), fu(k[j][3]));
    if (lane < 9) sts32(kp + 2560 + lane * 4, fu(lane < 8 ? k2048 : ksc));
  }
  if (wg) nb_sync(NB_PREP, 512);
  else { nb_arrive(NB_PREP, 512); nb_sync(0, 512); }
  if (warp >= 12) {
    asm volatile("setmaxnreg.dec.sync.aligned.u32 32;");
    if (warp == 12) {
      nb_sync(NB_KREAD, 160);
      asm volatile("fence.proxy.async.shared::cta;" ::: "memory");
      e_tma2d(sb + OFF_X + 2 * 16384, &mx, BAR(MB_FULL + 4), 256, rt * 256);
      uint32_t slot = sb + OFF_X + 3 * 16384;
#pragma unroll 1
      for (int n = 0; n < 11; n++) {
        mbar_spin(BAR(MB_EMPTY) + 8 * n);
        const int m = n + 5;
        e_tma2d(slot, &mx, BAR(MB_FULL) + 8 * m, (m & 7) * 64, rt * 256 + (m >> 3) * 128);
        slot = slot == sb + OFF_X + 4 * 16384 ? sb + OFF_X : slot + 16384;
        if (n == 7) e_prefetch(P.wo + (size_t)b * 2048, 4096);
      }
#pragma unroll 1
      for (int i = 0; i < 8; i++) {
        mbar_wait(BAR(MB_EMPTY + 10) + 8 * ((0x54332100u >> (4 * i)) & 7));
        const int w0 = (0x54736210u >> (4 * i)) & 7;
        e_tma3d(sb + OFF_W + w0 * 16384, &mo, BAR(MB_WO), 0, w0 * 64, (hp & 3) * 2);
      }
    } else {
      if (warp == 15) {
        const uint4 v0 = __ldg((const uint4*)P.wphi + hp * 64 + lane), v1 = __ldg((const uint4*)P.wphi + hp * 64 + 32 + lane);
        sts128(sb + OFF_PHI + (lane & 1) * 256 + (lane >> 1) * 16, v0.x, v0.y, v0.z, v0.w);
        sts128(sb + OFF_PHI + 512 + (lane & 1) * 256 + (lane >> 1) * 16, v1.x, v1.y, v1.z, v1.w);
        asm volatile("fence.proxy.async.shared::cta;" ::: "memory");
        __syncwarp();
        if (lane == 0) mbar_arrive(BAR(MB_AUX));
        mbar_wait(BAR(MB_EMPTY + ZERO_STEP));
        uint4* py = P.xs + X_Y + b * 1024 + lane;
#pragma unroll 1
        for (int i = 0; i < 1024; i += 32) st_x(py + i, 0, 0, 0, 0);
        nb_arrive(NB_YZ, 160);
        nb_arrive(NB_ODONE, 320);
        if (lane == 0) TS1(55);
        return;
      }
      uint32_t* const cnt = (uint32_t*)(P.xs + X_CNT) + (warp == 13 ? i8 : 8 + rt) * 32;
      const unsigned target = (ld_x32(cnt) & ~15u) + 16;
      if (warp == 13) {
        uint4* pp = P.xs + X_PART + (hp * 8 + rt) * 144 + lane;
#pragma unroll 1
        for (int i = 0; i < 144; i += 32) if (i + lane < 144) st_x(pp + i, 0, 0, 0, 0);
      }
      nb_sync(warp == 13 ? NB_INIT : NB_ODONE, warp == 13 ? 160 : 320);
      if (lane == 0) TS1(warp == 13 ? 49 : 56);
      asm volatile("fence.proxy.async.shared::cta;" ::: "memory");
      if (lane == 0) asm volatile("red.release.gpu.global.add.u32 [%0], 1;" ::"l"(cnt) : "memory");
      if (lane == 0) TS1(warp == 13 ? 50 : 57);
      const uint32_t* pc = (warp == 13 && (lane & 1)) ? (uint32_t*)(P.xs + X_CNT) + (b >> 4) * 32 : cnt;
#pragma unroll 1
      for (int i = 0; i < SPIN_MAX; i++) {
        unsigned v;
        asm volatile("ld.acquire.gpu.global.u32 %0, [%1];" : "=r"(v) : "l"(pc) : "memory");
        if (__all_sync(0xffffffffu, (int)(v - target) >= 0)) break;
      }
      if (lane == 0) TS1(warp == 13 ? 51 : 58);
      asm volatile("fence.proxy.async.global;" ::: "memory");
      if (warp == 13) {
        mbar_wait(BAR(MB_EMPTY + 11));
        e_expect(BAR(MB_UFULL), 4 * U_CH);
        e_bulk(sb + OFF_U, P.xs + X_UT + b * (U_CH / 4), 4 * U_CH, BAR(MB_UFULL));
      } else {
        const uint4* src = P.xs + X_O + (rt * 4 + (hp >> 2)) * 4096;
        e_expect(BAR(MB_OA), 14336);
        e_bulk(sb + OFF_STG0, src + 3200, 14336, BAR(MB_OA));
        e_expect(BAR(MB_OC), 32768);
        e_bulk(sb + OFF_X + 32768, src, 32768, BAR(MB_OC));
        nb_sync(NB_BDONE, 288);
        asm volatile("fence.proxy.async.shared::cta;" ::: "memory");
        e_expect(BAR(MB_OB), 18432);
        e_bulk(sb + OFF_U, src + 2048, 18432, BAR(MB_OB));
      }
    }
    return;
  }

  const int t = tid & 127;
  const int g = lane >> 2, c = lane & 3;
  {
    if (wg == 2) {
      asm volatile("setmaxnreg.inc.sync.aligned.u32 160;");
#pragma unroll
      for (int j = 0; j < 5; j++) { k[j][0] *= ksc; k[j][1] *= ksc; k[j][2] *= ksc; k[j][3] *= ksc; }
#pragma unroll 1
      for (int q = 0; q < 3; q++) {
        const uint32_t src = q ? tb + (q - 1) * 2608 : sb + OFF_X + 32768 + w * 4096;
        const float s = uf(lds32(src + 2592));
#pragma unroll
        for (int j = 0; j < 5; j++) {
          const uint4 v = lds128(src + j * 512 + lane * 16);
          k[j][0] = fmaf(uf(v.x), s, k[j][0]); k[j][1] = fmaf(uf(v.y), s, k[j][1]);
          k[j][2] = fmaf(uf(v.z), s, k[j][2]); k[j][3] = fmaf(uf(v.w), s, k[j][3]);
        }
        k2048 += uf(lds32(src + 2560 + (lane & 7) * 4));
        if (q == 0) nb_arrive(NB_KREAD, 160);
      }
#pragma unroll
      for (int o2 = 4; o2; o2 >>= 1) k2048 += __shfl_xor_sync(0xffffffffu, k2048, o2);
      if (lane == 0) k[0][0] += bf_lo(dsk);
      __syncwarp();
      TS(34);
      build_tables(tb, lane, k, k2048);
      TS(35);
      uint4* const g_y = P.xs + X_Y;
      conv_channel(sb + OFF_U + w * U_CH, tb, lane, g_y + (size_t)d * 256 + lane);
      nb_arrive(NB_BDONE, 288);
      TS(37);
      mbar_wait(BAR(MB_OA));
      const int lam = w * 8 + g;
      const uint4* src = g_y + (size_t)(oct * 32 + c * 8) * 256 + i8 * 32 + lam;
      uint4 v[8];
#pragma unroll 1
      for (int it = 0; it < SPIN_MAX; it++) {
        uint32_t m = 0xffffffffu;
#pragma unroll
        for (int i = 0; i < 8; i++) v[i] = ld_x(src + i * 256);
#pragma unroll
        for (int i = 0; i < 8; i++) m = min(m, v[i].x);
        if (__all_sync(0xffffffffu, m != 0)) break;
      }
      __nv_bfloat16* dst = P.out + (size_t)(i8 * 256 + (lam >> 2) * 16 + (lam & 3) * 2) * 1024 + 512 + oct * 32 + c * 8;
#pragma unroll
      for (int i = 0; i < 8; i++) *(uint4*)(dst + (size_t)((i >> 2) * 128 + ((i >> 1) & 1) * 8 + (i & 1)) * 1024) = tr_row(v, i);
      TS(38);
      GT(63);
      if (w == 0) TSDUMP(32);
      return;
    }
    if (wg == 1) {
      mbar_wait(BAR(MB_URAW));
      TS(48);
      uint4* dst = P.xs + X_UT + (i8 * 64 + g) * (U_CH / 16) + (c & 1) * (U_ODD / 16) + U_PAD / 16 + oct * 8 + w * 2 + (c >> 1);
      uint32_t r[8][4];
#pragma unroll
      for (int i = 0; i < 8; i++) ldsm4t(r[i], sb + OFF_STG0 + w * 4096 + lane * 128 + (((i ^ lane) & 7) << 4));
#pragma unroll
      for (int i = 0; i < 8; i++) dst[i * (U_CH / 2)] = make_uint4(r[i][0], r[i][1], r[i][2], r[i][3]);
      nb_arrive(NB_INIT, 160);
      if (lane == 0) mbar_arrive(BAR(MB_AUX));
      mbar_wait(BAR(MB_EMPTY + 4));
      mbar_spin(BAR(MB_EMPTY + 6));
    }
    TS(wg * 16 + 1);
  }

  float acc[2][48];
  {
    uint32_t fb = BAR(MB_FULL) + 64 * wg;
    uint32_t da = (uint32_t)mkdesc(sb + OFF_X, 16, 0, 0) + (wg ? 1024 : 3072), db = (uint32_t)mkdesc(sb + OFF_W, 4096, 0, 0);
    constexpr uint64_t ha = mkdesc(0, 0, 1024, 1), hb = mkdesc(0, 0, 512, 2);
#pragma unroll 1
    for (int kb = 0; kb < 8; kb++) {
      mbar_spin(fb);
      if (kb == 0) TS(wg * 16 + 2);
      WG_FENCE();
#pragma unroll
      for (int k = 0; k < 4; k++) {
        wgmma_ss_n96(acc[0], ha | (da + 2 * k), hb | (db + 64 * k), k ? 1 : kb);
        wgmma_ss_n96(acc[1], ha | (da + 2 * k + 512), hb | (db + 64 * k), k ? 1 : kb);
      }
      WG_COMMIT();
      WG_WAIT(1);
      if (kb > 0 && lane == 0) mbar_arrive(fb + 8 * (MB_EMPTY - MB_FULL - 1));
      fb += 8; db += 768;
      da = da == (uint32_t)mkdesc(sb + OFF_X + 65536, 16, 0, 0) ? da - 4096 : da + 1024;
    }
    WG_WAIT(0);
    if (lane == 0) mbar_arrive(fb + 8 * (MB_EMPTY - MB_FULL - 1));
    mbar_spin(fb + 8 * (MB_EMPTY - MB_FULL - 1));
  }
  TS(wg * 16 + 3);
  asm volatile("setmaxnreg.inc.sync.aligned.u32 160;");

  constexpr uint32_t stg0 = sb + OFF_STG0, stg1 = sb + OFF_X + 32768;
  const uint32_t sl = (wg ? stg1 : stg0) + w * 3072 + lane * 16;
  uint32_t pw[32], eq[32], vp[16];
  {
    uint4 af[8];
#pragma unroll
    for (int u = 0; u < 8; u++) {
      const float* a = acc[(u >> 1) & 1] + (u < 4 ? 16 : 0) + 8 * (u & 1);
      af[u] = make_uint4(pack_bf(a[0], a[1]), pack_bf(a[2], a[3]), pack_bf(a[4], a[5]), pack_bf(a[6], a[7]));
    }
    mbar_wait(BAR(MB_AUX));
    float p[8][8];
    WG_FENCE();
#pragma unroll
    for (int u = 0; u < 8; u++) wgmma_rs_n16(p[u], af[u], mkdesc(sb + OFF_PHI + (u & 1) * 512, 128, 256, 0), 0);
    WG_COMMIT();
#pragma unroll
    for (int i = 0; i < 16; i++) vp[i] = pack_bf(acc[i >> 3][32 + 2 * (i & 7)], acc[i >> 3][33 + 2 * (i & 7)]);
    WG_WAIT(0);
#pragma unroll
    for (int u = 0; u < 8; u++) {
      pw[4 * u] = pack_bf(p[u][0], p[u][2]); pw[4 * u + 1] = pack_bf(p[u][1], p[u][3]);
      pw[4 * u + 2] = pack_bf(p[u][4], p[u][6]); pw[4 * u + 3] = pack_bf(p[u][5], p[u][7]);
    }
  }
  uint32_t ek[32];
  if (wg == 0) {
#pragma unroll
    for (int i = 0; i < 16; i++) { const uint32_t x = pw[i]; pw[i] = pw[16 + i]; pw[16 + i] = x; }
  }
#pragma unroll 1
  for (int it = 0; it < 2; it++) {
#pragma unroll
    for (int i = 0; i < 32; i++) ek[i] = eq[i];
#pragma unroll
    for (int u = 0; u < 4; u++) dual_exp(pw + 4 * u, eq + 8 * u);
    if (it != wg) {
      TS(wg * 16 + 12);
      mbar_wait(BAR(MB_EMPTY + 15));
#pragma unroll
      for (int i = 0; i < 4; i++) stsm4(sl + (i >> 1) * 12288 + 2048 + (i & 1) * 512, vp[4 * i], vp[4 * i + 1], vp[4 * i + 2], vp[4 * i + 3]);
#pragma unroll
      for (int i = 0; i < 8; i++) norm_store(eq + 4 * i, sl + (i >> 2) * 12288 + (i & 3) * 512);
      if (wg) nb_arrive(NB_ST0, 256);
    }
#pragma unroll
    for (int i = 0; i < 16; i++) pw[i] = pw[i + 16];
  }
  TS(wg * 16 + 4);
  uint4* const g_part = P.xs + X_PART;
  uint4* const g_o = P.xs + X_O;
  const uint32_t kvs = stg0;
  if (wg == 0) {
#pragma unroll
    for (int i = 0; i < 32; i++) eq[i] = ek[i];
    nb_sync(NB_WG0, 128);
    mbar_wait(BAR(MB_UFULL));
    float kv[12], kw[12];
#pragma unroll
    for (int i = 0; i < 12; i++) kv[i] = kw[i] = 0.f;
    const int mi = lane >> 3;
    const uint32_t ao = w * 512 + (lane & 7) * 16 + ((mi & 1) * 2 + (mi >> 1)) * 128, bo = 2048 + (w >> 1) * 512 + lane * 16;
#pragma unroll 1
    for (int j = 0; j < 2; j++) {
      if (j) nb_sync(NB_ST0, 256);
      const uint32_t sg = j ? stg1 : stg0;
      uint32_t a[8][4], bb[8][4];
#pragma unroll
      for (int s = 0; s < 8; s++) { ldsm4t(a[s], sg + s * 3072 + ao); ldsm4t(bb[s], sg + s * 3072 + bo); }
#pragma unroll
      for (int s = 0; s < 8; s++) {
        float* o = (s & 1) ? kw : kv;
        mma(o[0], o[1], o[2], o[3], a[s][0], a[s][1], a[s][2], a[s][3], bb[s][0], bb[s][1]);
        mma(o[4], o[5], o[6], o[7], a[s][0], a[s][1], a[s][2], a[s][3], bb[s][2], bb[s][3]);
        mma(o[8], o[9], o[10], o[11], a[s][0], a[s][1], a[s][2], a[s][3], 0x3F803F80u, 0x3F803F80u);
      }
    }
#pragma unroll
    for (int i = 0; i < 12; i++) kv[i] += kw[i];
    uint4* pp = g_part + (size_t)(hp * 8 + rt) * 144;
    st_x(pp + t, nz(pack_bf(kv[0], kv[1])), pack_bf(kv[2], kv[3]), pack_bf(kv[4], kv[5]), pack_bf(kv[6], kv[7]));
    if (c < 2) st_x32((uint32_t*)(pp + 128) + w * 16 + c * 8 + g, nz(fu(c ? kv[10] : kv[8])));
    TS(5);
    const uint4* ps = g_part + (size_t)hp * 8 * 144 + t;
    const uint32_t* zs = (const uint32_t*)(g_part + (size_t)(hp * 8 + (lane >> 4) * 4) * 144 + 128) + w * 16 + (lane & 15);
    uint4 v[8];
    uint32_t zv[4];
#pragma unroll 1
    for (int it = 0; it < SPIN_MAX; it++) {
#pragma unroll
      for (int i = 0; i < 8; i++) v[i] = ld_x(ps + i * 144);
#pragma unroll
      for (int i = 0; i < 4; i++) zv[i] = ld_x32(zs + i * 576);
      uint32_t m = min(min(zv[0], zv[1]), min(zv[2], zv[3]));
#pragma unroll
      for (int i = 0; i < 8; i++) m = min(m, v[i].x);
      if (__all_sync(0xffffffffu, m != 0)) break;
    }
    float s4[4][4];
#pragma unroll
    for (int i = 0; i < 4; i++) s4[i][0] = s4[i][1] = s4[i][2] = s4[i][3] = 0.f;
    const uint32_t eye = (g >> 1) == c ? ((g & 1) ? 0x3F800000u : 0x3F80u) : 0u;
#pragma unroll
    for (int r = 0; r < 8; r++) {
      mma_k8(s4[(r & 1) * 2], v[r].x, v[r].y, eye);
      mma_k8(s4[(r & 1) * 2 + 1], v[r].z, v[r].w, eye);
    }
    float s[8];
#pragma unroll
    for (int i = 0; i < 8; i++) s[i] = s4[i >> 2][i & 3] + s4[2 + (i >> 2)][i & 3];
    float zsum = (uf(zv[0]) + uf(zv[1])) + (uf(zv[2]) + uf(zv[3]));
    zsum += __shfl_xor_sync(0xffffffffu, zsum, 16);
    stsm4(kvs + w * 512 + lane * 16, pack_bf(s[0], s[1]), pack_bf(s[2], s[3]), pack_bf(s[4], s[5]), pack_bf(s[6], s[7]));
    sts16(kvs + 2048 + (lane >> 4) * 128 + (w * 16 + (lane & 15)) * 2, lane < 16 ? pack_bf(zsum, 0.f) : 0x3F80u);
    TS(6);
  }
  nb_sync(NB_KV, 256);
  {
    uint32_t kb_[4][4], zb[8];
#pragma unroll
    for (int i = 0; i < 4; i++) ldsm4t(kb_[i], kvs + i * 512 + lane * 16);
#pragma unroll
    for (int i = 0; i < 8; i++) zb[i] = lds32(kvs + 2048 + (g & 1) * 128 + i * 16 + c * 4);
    uint32_t* od = (uint32_t*)(g_o + (size_t)((rt * 4 + wg * 2) * 32 + hp * 2) * 128) + w * 64 + lane;
#pragma unroll
    for (int mt = 0; mt < 2; mt++) {
#pragma unroll
      for (int h = 0; h < 2; h++) {
        const uint32_t* e = eq + 16 * mt + 8 * h;
        float n[8], nm[8], dp[4], dm[4];
        mma0(dp[0], dp[1], dp[2], dp[3], e[0], e[1], e[2], e[3], zb[4 * h], zb[4 * h + 1]);
        mma0(dm[0], dm[1], dm[2], dm[3], e[4], e[5], e[6], e[7], zb[4 * h + 2], zb[4 * h + 3]);
        mma0(n[0], n[1], n[2], n[3], e[0], e[1], e[2], e[3], kb_[2 * h][0], kb_[2 * h][1]);
        mma0(nm[0], nm[1], nm[2], nm[3], e[4], e[5], e[6], e[7], kb_[2 * h + 1][0], kb_[2 * h + 1][1]);
        mma0(n[4], n[5], n[6], n[7], e[0], e[1], e[2], e[3], kb_[2 * h][2], kb_[2 * h][3]);
        mma0(nm[4], nm[5], nm[6], nm[7], e[4], e[5], e[6], e[7], kb_[2 * h + 1][2], kb_[2 * h + 1][3]);
        const float q0 = dp[1] * rcp(dm[1]), q1 = dp[3] * rcp(dm[3]);
        const float r0 = rcp(fmaf(dm[0], q0, fmaf(dp[1], 1e-6f, dp[0]))), r1 = rcp(fmaf(dm[2], q1, fmaf(dp[3], 1e-6f, dp[2])));
#pragma unroll
        for (int i = 0; i < 8; i++) n[i] = fmaf(nm[i], (i & 2) ? q1 : q0, n[i]);
        od[h * 512] = pack_bf(n[0] * r0, n[1] * r0);
        od[h * 512 + 32] = pack_bf(n[2] * r1, n[3] * r1);
        od[h * 512 + 256] = pack_bf(n[4] * r0, n[5] * r0);
        od[h * 512 + 288] = pack_bf(n[6] * r1, n[7] * r1);
      }
      od += 16384;
    }
  }
  TS(wg * 16 + 7);
  nb_arrive(NB_ODONE, 320);
  if (wg) { if (w == 0) TSDUMP(16); return; }
  mbar_wait(BAR(MB_WO));
  mbar_wait(BAR(MB_OA));
  TS(8);
  nb_sync(NB_BDONE, 288);
  TS(9);
  float oc[64];
  {
    constexpr uint64_t ha = mkdesc(0, 0, 128, 0), hb = mkdesc(0, 0, 1024, 1);
    constexpr uint32_t da0 = (uint32_t)mkdesc(stg1, 1024, 0, 0), db0 = (uint32_t)mkdesc(sb + OFF_W, 8192, 0, 0);
#pragma unroll 1
    for (int j = 0; j < 8; j++) {
      const int kb = (j + 7) & 7;
      if ((j & 3) == 1) mbar_spin(j == 1 ? BAR(MB_OC) : BAR(MB_OB));
      WG_FENCE();
#pragma unroll
      for (int k = 0; k < 4; k++) wgmma_ss_n128(oc, ha | (da0 + 512 * kb + 128 * k), hb | (db0 + 1024 * kb + 128 * k), k ? 1 : j);
      WG_COMMIT();
    }
    WG_WAIT(0);
  }
  TS(10);
  nb_sync(NB_WG0, 128);
  const uint32_t ot = sb + OFF_W + w * 4096;
#pragma unroll
  for (int i = 0; i < 16; i += 2)
    stsm4(ot + (i >> 3) * 2048 + (lane & 15) * 128 + (((i + (lane >> 4)) ^ lane) & 7) * 16, pack_bf(oc[4 * i], oc[4 * i + 1]),
          pack_bf(oc[4 * i + 2], oc[4 * i + 3]), pack_bf(oc[4 * i + 4], oc[4 * i + 5]), pack_bf(oc[4 * i + 6], oc[4 * i + 7]));
  asm volatile("fence.proxy.async.shared::cta;" ::: "memory");
  __syncwarp();
  e_store3d(&mout, ot, (rt * 4 + (hp >> 2)) * 64 + w * 16, (hp & 3) * 2);
  TS(wg * 16 + 11);
  GT(61 + wg);
  if (w == 0) TSDUMP(0);
  if (w == 1) TSDUMP(48);
}

typedef CUresult (*EncodeFn)(CUtensorMap*, CUtensorMapDataType, cuuint32_t, void*, const cuuint64_t*, const cuuint64_t*,
                             const cuuint32_t*, const cuuint32_t*, CUtensorMapInterleave, CUtensorMapSwizzle,
                             CUtensorMapL2promotion, CUtensorMapFloatOOBfill);

}

extern "C" void kernel_launch(void* const* d_in, const int* in_sizes, int n_in, void* d_out, int out_size) {
  (void)in_sizes; (void)n_in; (void)out_size;
  void* fn = nullptr;
  cudaDriverEntryPointQueryResult qr;
  cudaGetDriverEntryPoint("cuTensorMapEncodeTiled", &fn, cudaEnableDefault, &qr);
  EncodeFn enc = (EncodeFn)fn;
  CUtensorMap mx, mw, mo, mu, mout, mw4;
  const cuuint32_t es[5] = {1, 1, 1, 1, 1};
  {
    cuuint64_t dims[2] = {512, 2048}, st[1] = {1024};
    cuuint32_t box[2] = {64, 128};
    enc(&mx, CU_TENSOR_MAP_DATA_TYPE_BFLOAT16, 2, d_in[0], dims, st, box, es, CU_TENSOR_MAP_INTERLEAVE_NONE,
        CU_TENSOR_MAP_SWIZZLE_128B, CU_TENSOR_MAP_L2_PROMOTION_L2_128B, CU_TENSOR_MAP_FLOAT_OOB_FILL_NONE);
  }
  {
    cuuint64_t dims[3] = {512, 512, 3}, st[2] = {3072, 1024};
    cuuint32_t box[3] = {32, 64, 3};
    enc(&mw, CU_TENSOR_MAP_DATA_TYPE_BFLOAT16, 3, d_in[1], dims, st, box, es, CU_TENSOR_MAP_INTERLEAVE_NONE,
        CU_TENSOR_MAP_SWIZZLE_64B, CU_TENSOR_MAP_L2_PROMOTION_L2_128B, CU_TENSOR_MAP_FLOAT_OOB_FILL_NONE);
  }
  {
    cuuint64_t dims[3] = {64, 512, 8}, st[2] = {1024, 128};
    cuuint32_t box[3] = {64, 64, 2};
    enc(&mo, CU_TENSOR_MAP_DATA_TYPE_BFLOAT16, 3, d_in[3], dims, st, box, es, CU_TENSOR_MAP_INTERLEAVE_NONE,
        CU_TENSOR_MAP_SWIZZLE_128B, CU_TENSOR_MAP_L2_PROMOTION_L2_128B, CU_TENSOR_MAP_FLOAT_OOB_FILL_NONE);
  }
  {
    cuuint64_t dims[5] = {512, 2, 4, 4, 64}, st[4] = {1024, 8192, 2048, 32768};
    cuuint32_t box[5] = {64, 2, 4, 4, 4};
    enc(&mu, CU_TENSOR_MAP_DATA_TYPE_BFLOAT16, 5, d_in[4], dims, st, box, es, CU_TENSOR_MAP_INTERLEAVE_NONE,
        CU_TENSOR_MAP_SWIZZLE_128B, CU_TENSOR_MAP_L2_PROMOTION_L2_128B, CU_TENSOR_MAP_FLOAT_OOB_FILL_NONE);
  }
  {
    cuuint64_t dims[3] = {64, 2048, 16}, st[2] = {2048, 128};
    cuuint32_t box[3] = {64, 16, 2};
    enc(&mout, CU_TENSOR_MAP_DATA_TYPE_BFLOAT16, 3, d_out, dims, st, box, es, CU_TENSOR_MAP_INTERLEAVE_NONE,
        CU_TENSOR_MAP_SWIZZLE_128B, CU_TENSOR_MAP_L2_PROMOTION_NONE, CU_TENSOR_MAP_FLOAT_OOB_FILL_NONE);
  }
  {
    cuuint64_t dims[4] = {512, 64, 3, 8}, st[3] = {3072, 1024, 64 * 3072};
    cuuint32_t box[4] = {32, 64, 3, 4};
    enc(&mw4, CU_TENSOR_MAP_DATA_TYPE_BFLOAT16, 4, d_in[1], dims, st, box, es, CU_TENSOR_MAP_INTERLEAVE_NONE,
        CU_TENSOR_MAP_SWIZZLE_64B, CU_TENSOR_MAP_L2_PROMOTION_L2_128B, CU_TENSOR_MAP_FLOAT_OOB_FILL_NONE);
  }
  Params P;
  P.x = (const __nv_bfloat16*)d_in[0];
  P.wphi = (const __nv_bfloat16*)d_in[2];
  P.wo = (const __nv_bfloat16*)d_in[3];
  P.logA = (const __nv_bfloat16*)d_in[5];
  P.Aim = (const __nv_bfloat16*)d_in[6];
  P.Cre = (const __nv_bfloat16*)d_in[7];
  P.Cim = (const __nv_bfloat16*)d_in[8];
  P.logdt = (const __nv_bfloat16*)d_in[9];
  P.Dskip = (const __nv_bfloat16*)d_in[10];
  P.out = (__nv_bfloat16*)d_out;
  cudaGetSymbolAddress((void**)&P.xs, g_x);
  P.ts = nullptr;
  cudaFuncSetAttribute(fused_kernel, cudaFuncAttributeMaxDynamicSharedMemorySize, SMEM_BYTES);
  fused_kernel<<<NCTA, NTHREADS, SMEM_BYTES>>>(P, mx, mw, mo, mu, mout, mw4);
}
```

```cpp
#include <cuda_runtime.h>
#include <cuda_bf16.h>
#include <cuda_fp16.h>
#include <cuda.h>
#include <stdint.h>

#define DBG_TS 0

namespace {

constexpr int NTHREADS = 512;
constexpr int NCTA = 128;
constexpr int OFF_W = 0;
constexpr int OFF_X = 98304;
constexpr int OFF_U = OFF_X + 65536;
constexpr int U_CH = 4416, U_ODD = 2240, U_PAD = 128;
constexpr int OFF_STG0 = OFF_U + 18432;
constexpr int OFF_T = OFF_STG0 + 24576;
constexpr int T_CH = 5216;
constexpr int T_D = 0;
constexpr int T_5 = 2144;
constexpr int T_3 = T_5 + 384;
constexpr int T_7 = T_5 + 1024;
constexpr int T_9 = T_7 + 320;
constexpr int T_KC = T_9 + 320;
constexpr int T_ST = T_5 - 1024;
constexpr int OFF_PHI = OFF_T + 4 * T_CH;
constexpr int OFF_BAR = OFF_PHI + 1024;
constexpr int SMEM_BYTES = OFF_BAR + 512 + 256 * DBG_TS;
constexpr uint32_t SB = 1024;
static_assert(T_KC + 2 * 656 <= T_CH, "table size");
static_assert(SMEM_BYTES <= 232448, "smem");
constexpr int MB_URAW = 0, MB_FULL = 1  , MB_WO = 17, MB_UFULL = 18, MB_OA = 19, MB_OB = 20, MB_OC = 21,
              MB_EMPTY = 22  , MB_AUX = 38;
__host__ __device__ constexpr uint32_t BAR(int i) { return SB + OFF_BAR + 8 * i; }
constexpr int NB_WG0 = 1, NB_ODONE = 2, NB_ST0 = 3  , NB_KV = 5, NB_YZ = 6, NB_INIT = 7, NB_PREP = 8, NB_PROD = 9, NB_KREAD = 10, NB_BDONE = 11, NB_ZERO = 12;
#define U_AT 2
#define ZERO_STEP 15
constexpr int SPIN_MAX = 1 << 16;

constexpr int X_CNT = 0;
constexpr int X_PART = 128;
constexpr int X_O = X_PART + 16 * 8 * 144;
constexpr int X_Y = X_O + 32 * 32 * 128;
constexpr int X_UT = X_Y + 512 * 8 * 32;
constexpr int X_SIZE = X_UT + 512 * (U_CH / 16);
__device__ __align__(128) uint4 g_x[X_SIZE];
extern __shared__ uint8_t smem_raw[];
#define TS(i) do {} while (0)
#define TS1(i) do {} while (0)
#define GT(i) do {} while (0)
#define TSDUMP(base) do {} while (0)

__device__ __forceinline__ uint32_t smem_u32(const void* p) { return (uint32_t)__cvta_generic_to_shared(p); }
__device__ __forceinline__ void mbar_arrive(uint32_t b) {
  asm volatile("mbarrier.arrive.shared::cta.b64 _, [%0];" ::"r"(b) : "memory");
}
__device__ __forceinline__ void mbar_wait(uint32_t b) {
  uint32_t done = 0;
#pragma unroll 1
  for (int i = 0; i < SPIN_MAX && !done; i++) {
    asm volatile("{\n.reg .pred p;\nmbarrier.try_wait.parity.shared::cta.b64 p, [%1], 0, 4000;\nselp.u32 %0, 1, 0, p;\n}\n"
                 : "=r"(done) : "r"(b) : "memory");
  }
}
__device__ __forceinline__ void mbar_spin(uint32_t b) {
  uint32_t done = 0;
#pragma unroll 1
  for (int i = 0; i < (SPIN_MAX << 4) && !done; i++) {
    asm volatile("{\n.reg .pred p;\nmbarrier.try_wait.parity.shared::cta.b64 p, [%1], 0;\nselp.u32 %0, 1, 0, p;\n}\n"
                 : "=r"(done) : "r"(b) : "memory");
  }
}
__device__ __forceinline__ void mbar_init(uint32_t b, int n) {
  asm volatile("mbarrier.init.shared::cta.b64 [%0], %1;" ::"r"(b), "r"(n) : "memory");
}
__device__ __forceinline__ void mbar_expect(uint32_t b, int bytes) {
  asm volatile("mbarrier.arrive.expect_tx.shared::cta.b64 _, [%0], %1;" ::"r"(b), "r"(bytes) : "memory");
}
__device__ __forceinline__ void nb_sync(int id, int n) { asm volatile("bar.sync %0, %1;" ::"r"(id), "r"(n) : "memory"); }
__device__ __forceinline__ void nb_arrive(int id, int n) { asm volatile("bar.arrive %0, %1;" ::"r"(id), "r"(n) : "memory"); }
#define ELECT "{\n.reg .pred p;\nelect.sync _|p, 0xffffffff;\n@p "
__device__ __forceinline__ void e_expect(uint32_t b, int bytes) {
  asm volatile(ELECT "mbarrier.arrive.expect_tx.shared::cta.b64 _, [%0], %1;\n}\n" ::"r"(b), "r"(bytes) : "memory");
}
__device__ __forceinline__ void e_tma2d(uint32_t dst, const CUtensorMap* m, uint32_t bar, int c0, int c1) {
  asm volatile(ELECT "cp.async.bulk.tensor.2d.shared::cluster.global.mbarrier::complete_tx::bytes [%0], [%1, {%3,%4}], [%2];\n}\n"
               ::"r"(dst), "l"(m), "r"(bar), "r"(c0), "r"(c1) : "memory");
}
__device__ __forceinline__ void e_tma3d(uint32_t dst, const CUtensorMap* m, uint32_t bar, int c0, int c1, int c2) {
  asm volatile(ELECT "cp.async.bulk.tensor.3d.shared::cluster.global.mbarrier::complete_tx::bytes [%0], [%1, {%3,%4,%5}], [%2];\n}\n"
               ::"r"(dst), "l"(m), "r"(bar), "r"(c0), "r"(c1), "r"(c2) : "memory");
}
__device__ __forceinline__ void e_tma4d(uint32_t dst, const CUtensorMap* m, uint32_t bar, int c0, int c3) {
  asm volatile(ELECT "cp.async.bulk.tensor.4d.shared::cluster.global.mbarrier::complete_tx::bytes [%0], [%1, {%3,%5,%5,%4}], [%2];\n}\n"
               ::"r"(dst), "l"(m), "r"(bar), "r"(c0), "r"(c3), "r"(0) : "memory");
}
__device__ __forceinline__ void e_tma5d(uint32_t dst, const CUtensorMap* m, uint32_t bar, int c0, int c4) {
  asm volatile(ELECT "cp.async.bulk.tensor.5d.shared::cluster.global.mbarrier::complete_tx::bytes [%0], [%1, {%3,%5,%5,%5,%4}], [%2];\n}\n"
               ::"r"(dst), "l"(m), "r"(bar), "r"(c0), "r"(c4), "r"(0) : "memory");
}
__device__ __forceinline__ void e_bulk(uint32_t dst, const void* src, int bytes, uint32_t bar) {
  asm volatile(ELECT "cp.async.bulk.shared::cluster.global.mbarrier::complete_tx::bytes [%0], [%1], %2, [%3];\n}\n"
               ::"r"(dst), "l"(src), "r"(bytes), "r"(bar) : "memory");
}
__device__ __forceinline__ void e_prefetch(const void* p, int bytes) {
  asm volatile(ELECT "cp.async.bulk.prefetch.L2.global [%0], %1;\n}\n" ::"l"(p), "r"(bytes) : "memory");
}
__device__ __forceinline__ void e_store3d(const CUtensorMap* m, uint32_t src, int c1, int c2) {
  asm volatile(ELECT "cp.async.bulk.tensor.3d.global.shared::cta.bulk_group [%0, {%4,%2,%3}], [%1];\n"
               "@p cp.async.bulk.commit_group;\n@p cp.async.bulk.wait_group.read 0;\n}\n"
               ::"l"(m), "r"(src), "r"(c1), "r"(c2), "r"(0) : "memory");
}
__host__ __device__ constexpr uint64_t mkdesc(uint32_t addr, uint32_t lbo, uint32_t sbo, int swz) {
  return (uint64_t)((addr & 0x3FFFF) >> 4) | ((uint64_t)(lbo >> 4) << 16) | ((uint64_t)(sbo >> 4) << 32) |
         ((uint64_t)swz << 62);
}
#define WG_FENCE() asm volatile("wgmma.fence.sync.aligned;" ::: "memory")
#define WG_COMMIT() asm volatile("wgmma.commit_group.sync.aligned;" ::: "memory")
#define WG_WAIT(n) asm volatile("wgmma.wait_group.sync.aligned " #n ";" ::: "memory")

__device__ __forceinline__ void mma(float& d0, float& d1, float& d2, float& d3, uint32_t a0, uint32_t a1, uint32_t a2,
                                    uint32_t a3, uint32_t b0, uint32_t b1) {
  asm volatile("mma.sync.aligned.m16n8k16.row.col.f32.bf16.bf16.f32 {%0,%1,%2,%3},{%4,%5,%6,%7},{%8,%9},{%0,%1,%2,%3};"
               : "+f"(d0), "+f"(d1), "+f"(d2), "+f"(d3)
               : "r"(a0), "r"(a1), "r"(a2), "r"(a3), "r"(b0), "r"(b1));
}
__device__ __forceinline__ void mmac(float (&d)[4], uint32_t a0, uint32_t a1, uint32_t a2, uint32_t a3, uint32_t b0,
                                     uint32_t b1, const float (&c)[4]) {
  asm volatile("mma.sync.aligned.m16n8k16.row.col.f32.bf16.bf16.f32 {%0,%1,%2,%3},{%4,%5,%6,%7},{%8,%9},{%10,%11,%12,%13};"
               : "=f"(d[0]), "=f"(d[1]), "=f"(d[2]), "=f"(d[3])
               : "r"(a0), "r"(a1), "r"(a2), "r"(a3), "r"(b0), "r"(b1), "f"(c[0]), "f"(c[1]), "f"(c[2]), "f"(c[3]));
}
__device__ __forceinline__ void mma_p(int p, float (&d)[4], uint32_t a0, uint32_t a1, uint32_t a2, uint32_t a3, uint32_t b0, uint32_t b1) {
  asm volatile("{\n.reg .pred q;\nsetp.ne.b32 q, %10, 0;\n"
               "@q mma.sync.aligned.m16n8k16.row.col.f32.bf16.bf16.f32 {%0,%1,%2,%3},{%4,%5,%6,%7},{%8,%9},{%0,%1,%2,%3};\n}\n"
               : "+f"(d[0]), "+f"(d[1]), "+f"(d[2]), "+f"(d[3])
               : "r"(a0), "r"(a1), "r"(a2), "r"(a3), "r"(b0), "r"(b1), "r"(p));
}
__device__ __forceinline__ void mmac_p(int p, float (&d)[4], uint32_t a0, uint32_t a1, uint32_t a2, uint32_t a3, uint32_t b0,
                                       uint32_t b1, const float (&c)[4]) {
  asm volatile("{\n.reg .pred q;\nsetp.ne.b32 q, %14, 0;\n"
               "@q mma.sync.aligned.m16n8k16.row.col.f32.bf16.bf16.f32 {%0,%1,%2,%3},{%4,%5,%6,%7},{%8,%9},{%10,%11,%12,%13};\n}\n"
               : "+f"(d[0]), "+f"(d[1]), "+f"(d[2]), "+f"(d[3])
               : "r"(a0), "r"(a1), "r"(a2), "r"(a3), "r"(b0), "r"(b1), "f"(c[0]), "f"(c[1]), "f"(c[2]), "f"(c[3]), "r"(p));
}
__device__ __forceinline__ void mma_h(float (&d)[4], const uint32_t (&a)[4], uint32_t b0, uint32_t b1) {
  asm volatile("mma.sync.aligned.m16n8k16.row.col.f32.f16.f16.f32 {%0,%1,%2,%3},{%4,%5,%6,%7},{%8,%9},{%0,%1,%2,%3};"
               : "+f"(d[0]), "+f"(d[1]), "+f"(d[2]), "+f"(d[3]) : "r"(a[0]), "r"(a[1]), "r"(a[2]), "r"(a[3]), "r"(b0), "r"(b1));
}
__device__ __forceinline__ void mma_k8(float (&d)[4], uint32_t a0, uint32_t a1, uint32_t b0) {
  asm volatile("mma.sync.aligned.m16n8k8.row.col.f32.bf16.bf16.f32 {%0,%1,%2,%3},{%4,%5},{%6},{%0,%1,%2,%3};"
               : "+f"(d[0]), "+f"(d[1]), "+f"(d[2]), "+f"(d[3]) : "r"(a0), "r"(a1), "r"(b0));
}
__device__ __forceinline__ void mma0(float& d0, float& d1, float& d2, float& d3, uint32_t a0, uint32_t a1, uint32_t a2,
                                     uint32_t a3, uint32_t b0, uint32_t b1) {
  asm volatile("mma.sync.aligned.m16n8k16.row.col.f32.bf16.bf16.f32 {%0,%1,%2,%3},{%4,%5,%6,%7},{%8,%9},{%10,%10,%10,%10};"
               : "=f"(d0), "=f"(d1), "=f"(d2), "=f"(d3)
               : "r"(a0), "r"(a1), "r"(a2), "r"(a3), "r"(b0), "r"(b1), "f"(0.f));
}
__device__ __forceinline__ uint32_t pack_bf(float lo, float hi) {
  uint32_t r;
  asm("cvt.rn.bf16x2.f32 %0, %1, %2;" : "=r"(r) : "f"(hi), "f"(lo));
  return r;
}
__device__ __forceinline__ float bf_lo(uint32_t w) { return __uint_as_float(w << 16); }
__device__ __forceinline__ float bf_hi(uint32_t w) { return __uint_as_float(w & 0xffff0000u); }
__device__ __forceinline__ float bf_round(float x) { return __bfloat162float(__float2bfloat16_rn(x)); }
__device__ __forceinline__ uint32_t bmax2(uint32_t a, uint32_t b) {
  uint32_t r; asm("max.bf16x2 %0, %1, %2;" : "=r"(r) : "r"(a), "r"(b)); return r;
}
__device__ __forceinline__ uint32_t bmin2(uint32_t a, uint32_t b) {
  uint32_t r; asm("min.bf16x2 %0, %1, %2;" : "=r"(r) : "r"(a), "r"(b)); return r;
}
__device__ __forceinline__ float ex2(float x) { float r; asm("ex2.approx.ftz.f32 %0, %1;" : "=f"(r) : "f"(x)); return r; }
__device__ __forceinline__ float rcp(float x) { float r; asm("rcp.approx.ftz.f32 %0, %1;" : "=f"(r) : "f"(x)); return r; }
__device__ __forceinline__ void ldsm4(uint32_t (&r)[4], uint32_t a) {
  asm volatile("ldmatrix.sync.aligned.m8n8.x4.shared.b16 {%0,%1,%2,%3}, [%4];"
               : "=r"(r[0]), "=r"(r[1]), "=r"(r[2]), "=r"(r[3]) : "r"(a) : "memory");
}
__device__ __forceinline__ void ldsm4t(uint32_t (&r)[4], uint32_t a) {
  asm volatile("ldmatrix.sync.aligned.m8n8.x4.trans.shared.b16 {%0,%1,%2,%3}, [%4];"
               : "=r"(r[0]), "=r"(r[1]), "=r"(r[2]), "=r"(r[3]) : "r"(a) : "memory");
}
__device__ __forceinline__ void stsm4(uint32_t a, uint32_t r0, uint32_t r1, uint32_t r2, uint32_t r3) {
  asm volatile("stmatrix.sync.aligned.m8n8.x4.shared.b16 [%0], {%1,%2,%3,%4};"
               ::"r"(a), "r"(r0), "r"(r1), "r"(r2), "r"(r3) : "memory");
}
__device__ __forceinline__ uint32_t lds32(uint32_t a) {
  uint32_t r; asm volatile("ld.shared.u32 %0, [%1];" : "=r"(r) : "r"(a) : "memory"); return r;
}
__device__ __forceinline__ uint32_t lds16(uint32_t a) {
  uint32_t r; asm volatile("{\n.reg .u16 h;\nld.shared.u16 h, [%1];\ncvt.u32.u16 %0, h;\n}\n" : "=r"(r) : "r"(a) : "memory"); return r;
}
__device__ __forceinline__ uint2 lds64(uint32_t a) {
  uint2 r; asm volatile("ld.shared.v2.u32 {%0,%1}, [%2];" : "=r"(r.x), "=r"(r.y) : "r"(a) : "memory"); return r;
}
__device__ __forceinline__ uint4 lds128(uint32_t a) {
  uint4 r;
  asm volatile("ld.shared.v4.u32 {%0,%1,%2,%3}, [%4];" : "=r"(r.x), "=r"(r.y), "=r"(r.z), "=r"(r.w) : "r"(a) : "memory");
  return r;
}
__device__ __forceinline__ void sts32(uint32_t a, uint32_t v) { asm volatile("st.shared.u32 [%0], %1;" ::"r"(a), "r"(v) : "memory"); }
__device__ __forceinline__ void sts16(uint32_t a, uint32_t v) {
  asm volatile("{\n.reg .u16 h;\ncvt.u16.u32 h, %1;\nst.shared.u16 [%0], h;\n}\n" ::"r"(a), "r"(v) : "memory");
}
__device__ __forceinline__ void sts64(uint32_t a, uint32_t x, uint32_t y) {
  asm volatile("st.shared.v2.u32 [%0], {%1,%2};" ::"r"(a), "r"(x), "r"(y) : "memory");
}
__device__ __forceinline__ void sts128(uint32_t a, uint32_t x, uint32_t y, uint32_t z, uint32_t w) {
  asm volatile("st.shared.v4.u32 [%0], {%1,%2,%3,%4};" ::"r"(a), "r"(x), "r"(y), "r"(z), "r"(w) : "memory");
}
__device__ __forceinline__ uint4 ld_x(const uint4* p) {
  uint4 r;
  asm volatile("{\n.reg .b128 t;\nld.relaxed.gpu.global.b128 t, [%4];\nmov.b128 {%0,%1,%2,%3}, t;\n}\n"
               : "=r"(r.x), "=r"(r.y), "=r"(r.z), "=r"(r.w) : "l"(p) : "memory");
  return r;
}
__device__ __forceinline__ uint32_t ld_x32(const uint32_t* p) {
  uint32_t r; asm volatile("ld.relaxed.gpu.global.u32 %0, [%1];" : "=r"(r) : "l"(p) : "memory"); return r;
}
__device__ __forceinline__ void st_x(uint4* p, uint32_t x, uint32_t y, uint32_t z, uint32_t w) {
  asm volatile("{\n.reg .b128 t;\nmov.b128 t, {%1,%2,%3,%4};\nst.relaxed.gpu.global.b128 [%0], t;\n}\n"
               ::"l"(p), "r"(x), "r"(y), "r"(z), "r"(w) : "memory");
}
__device__ __forceinline__ void st_x_p(int p, uint4* a, uint32_t x, uint32_t y, uint32_t z, uint32_t w) {
  asm volatile("{\n.reg .b128 t;\n.reg .pred q;\nsetp.ne.b32 q, %5, 0;\nmov.b128 t, {%1,%2,%3,%4};\n@q st.relaxed.gpu.global.b128 [%0], t;\n}\n"
               ::"l"(a), "r"(x), "r"(y), "r"(z), "r"(w), "r"(p) : "memory");
}
__device__ __forceinline__ void sts64_p(int p, uint32_t a, uint32_t x, uint32_t y) {
  asm volatile("{\n.reg .pred q;\nsetp.ne.b32 q, %3, 0;\n@q st.shared.v2.u32 [%0], {%1,%2};\n}\n" ::"r"(a), "r"(x), "r"(y), "r"(p) : "memory");
}
__device__ __forceinline__ void st_x32(uint32_t* p, uint32_t x) {
  asm volatile("st.relaxed.gpu.global.u32 [%0], %1;" ::"l"(p), "r"(x) : "memory");
}
__device__ __forceinline__ uint32_t nz(uint32_t w) { return max(w, 1u); }
__device__ __forceinline__ uint32_t fu(float x) { return __float_as_uint(x); }
__device__ __forceinline__ float uf(uint32_t x) { return __uint_as_float(x); }

__device__ __forceinline__ void wgmma_ss_n96(float (&d)[48], uint64_t da, uint64_t db, int sc) {
  asm volatile("{\n.reg .pred p;\nsetp.ne.b32 p, %50, 0;\n"
      "wgmma.mma_async.sync.aligned.m64n96k16.f32.bf16.bf16 "
      "{%0,%1,%2,%3,%4,%5,%6,%7,%8,%9,%10,%11,%12,%13,%14,%15,%16,%17,%18,%19,%20,%21,%22,%23,%24,%25,%26,%27,%28,%29,%30,%31,%32,%33,%34,%35,%36,%37,%38,%39,%40,%41,%42,%43,%44,%45,%46,%47}, "
      "%48, %49, p, 1, 1, 0, 1;\n}\n"
      : "+f"(d[0]), "+f"(d[1]), "+f"(d[2]), "+f"(d[3]), "+f"(d[4]), "+f"(d[5]), "+f"(d[6]), "+f"(d[7]),
        "+f"(d[8]), "+f"(d[9]), "+f"(d[10]), "+f"(d[11]), "+f"(d[12]), "+f"(d[13]), "+f"(d[14]), "+f"(d[15]),
        "+f"(d[16]), "+f"(d[17]), "+f"(d[18]), "+f"(d[19]), "+f"(d[20]), "+f"(d[21]), "+f"(d[22]), "+f"(d[23]),
        "+f"(d[24]), "+f"(d[25]), "+f"(d[26]), "+f"(d[27]), "+f"(d[28]), "+f"(d[29]), "+f"(d[30]), "+f"(d[31]),
        "+f"(d[32]), "+f"(d[33]), "+f"(d[34]), "+f"(d[35]), "+f"(d[36]), "+f"(d[37]), "+f"(d[38]), "+f"(d[39]),
        "+f"(d[40]), "+f"(d[41]), "+f"(d[42]), "+f"(d[43]), "+f"(d[44]), "+f"(d[45]), "+f"(d[46]), "+f"(d[47])
      : "l"(da), "l"(db), "r"(sc));
}

__device__ __forceinline__ void wgmma_ss_n128(float (&d)[64], uint64_t da, uint64_t db, int sc) {
  asm volatile("{\n.reg .pred p;\nsetp.ne.b32 p, %66, 0;\n"
      "wgmma.mma_async.sync.aligned.m64n128k16.f32.bf16.bf16 "
      "{%0,%1,%2,%3,%4,%5,%6,%7,%8,%9,%10,%11,%12,%13,%14,%15,%16,%17,%18,%19,%20,%21,%22,%23,%24,%25,%26,%27,%28,%29,%30,%31,%32,%33,%34,%35,%36,%37,%38,%39,%40,%41,%42,%43,%44,%45,%46,%47,%48,%49,%50,%51,%52,%53,%54,%55,%56,%57,%58,%59,%60,%61,%62,%63}, "
      "%64, %65, p, 1, 1, 0, 1;\n}\n"
      : "+f"(d[0]), "+f"(d[1]), "+f"(d[2]), "+f"(d[3]), "+f"(d[4]), "+f"(d[5]), "+f"(d[6]), "+f"(d[7]),
        "+f"(d[8]), "+f"(d[9]), "+f"(d[10]), "+f"(d[11]), "+f"(d[12]), "+f"(d[13]), "+f"(d[14]), "+f"(d[15]),
        "+f"(d[16]), "+f"(d[17]), "+f"(d[18]), "+f"(d[19]), "+f"(d[20]), "+f"(d[21]), "+f"(d[22]), "+f"(d[23]),
        "+f"(d[24]), "+f"(d[25]), "+f"(d[26]), "+f"(d[27]), "+f"(d[28]), "+f"(d[29]), "+f"(d[30]), "+f"(d[31]),
        "+f"(d[32]), "+f"(d[33]), "+f"(d[34]), "+f"(d[35]), "+f"(d[36]), "+f"(d[37]), "+f"(d[38]), "+f"(d[39]),
        "+f"(d[40]), "+f"(d[41]), "+f"(d[42]), "+f"(d[43]), "+f"(d[44]), "+f"(d[45]), "+f"(d[46]), "+f"(d[47]),
        "+f"(d[48]), "+f"(d[49]), "+f"(d[50]), "+f"(d[51]), "+f"(d[52]), "+f"(d[53]), "+f"(d[54]), "+f"(d[55]),
        "+f"(d[56]), "+f"(d[57]), "+f"(d[58]), "+f"(d[59]), "+f"(d[60]), "+f"(d[61]), "+f"(d[62]), "+f"(d[63])
      : "l"(da), "l"(db), "r"(sc));
}

__device__ __forceinline__ void wgmma_rs_n16(float (&d)[8], const uint4& a, uint64_t db, int sc) {
  asm volatile("{\n.reg .pred p;\nsetp.ne.b32 p, %13, 0;\n"
      "wgmma.mma_async.sync.aligned.m64n16k16.f32.bf16.bf16 "
      "{%0,%1,%2,%3,%4,%5,%6,%7}, "
      "{%8,%9,%10,%11}, %12, p, 1, 1, 1;\n}\n"
      : "+f"(d[0]), "+f"(d[1]), "+f"(d[2]), "+f"(d[3]), "+f"(d[4]), "+f"(d[5]), "+f"(d[6]), "+f"(d[7])
      : "r"(a.x), "r"(a.y), "r"(a.z), "r"(a.w), "l"(db), "r"(sc));
}

struct Params {
  const __nv_bfloat16 *logA, *Aim, *Cre, *Cim, *logdt, *Dskip, *x, *wphi, *wo;
  __nv_bfloat16* out;
  uint4* xs;
  long long* ts;
};

__device__ __forceinline__ uint4 tr_row(const uint4 (&v)[8], int i) {
  uint32_t o[4];
#pragma unroll
  for (int m = 0; m < 4; m++) {
    const uint4 &ra = v[2 * m], &rb = v[2 * m + 1];
    const int k = i >> 1;
    const uint32_t xa = k == 0 ? ra.x : k == 1 ? ra.y : k == 2 ? ra.z : ra.w;
    const uint32_t xb = k == 0 ? rb.x : k == 1 ? rb.y : k == 2 ? rb.z : rb.w;
    o[m] = __byte_perm(xa, xb, (i & 1) ? 0x7632 : 0x5410);
  }
  return make_uint4(o[0], o[1], o[2], o[3]);
}

struct cpx { float r, i; };
__device__ __forceinline__ cpx csq(cpx a) { return {a.r * a.r - a.i * a.i, 2.f * (a.r * a.i)}; }
__device__ __forceinline__ cpx polar(float e, float t) {
  const float m = ex2(e);
  return {m * __cosf(t), m * __sinf(t)};
}

struct KgenRaw { unsigned short la, ai, cr, ci, ldt; };
__device__ __forceinline__ KgenRaw kgen_load(const Params& P, int d, int unit, int lane) {
  const int o = d * 128 + unit * 32 + lane;
  return {__ldg((const unsigned short*)P.logA + o), __ldg((const unsigned short*)P.Aim + o), __ldg((const unsigned short*)P.Cre + o),
          __ldg((const unsigned short*)P.Cim + o), __ldg((const unsigned short*)P.logdt + d)};
}
struct hmul { __half2 a, b; };
__device__ __forceinline__ hmul mk_mul(cpx w) {
  uint32_t b;
  asm("{\n.reg .f32 n;\nneg.ftz.f32 n, %1;\ncvt.rn.f16x2.f32 %0, %2, n;\n}\n" : "=r"(b) : "f"(w.i), "f"(w.r));
  return {__floats2half2_rn(w.r, w.i), *(const __half2*)&b};
}
__device__ __forceinline__ __half2 hcm(__half2 z, const hmul& w) { return __hfma2(__high2half2(z), w.b, __hmul2(__low2half2(z), w.a)); }
__device__ __forceinline__ uint32_t hu(__half2 v) { return *(const uint32_t*)&v; }

struct KgenAddr { uint32_t sa, sb, lb, lc, la; };
__device__ __forceinline__ KgenAddr kgen_addr(int lane, uint32_t buf) {
  KgenAddr a;
  a.sa = buf + (lane & 7) * 128 + ((((lane >> 3) ^ lane) & 7) << 4);
  a.lb = buf + (lane >> 3) * 128 + (((lane ^ (lane >> 3)) & 7) << 4);
  a.la = buf + ((lane >> 3) & 1) * 1024 + (lane >> 4) * 128 + (((lane ^ (lane >> 4)) & 7) << 4);
  a.sb = a.sa ^ 64; a.lc = a.lb ^ 64;
  asm volatile("" : "+r"(a.sa), "+r"(a.sb), "+r"(a.lb), "+r"(a.lc), "+r"(a.la));
  return a;
}
__device__ __forceinline__ void kgen_unit(const KgenRaw& r, const KgenAddr& ad, uint32_t zero, float (&k)[5][4], float& k2048, float& sc) {
  const float dt = bf_round(expf(bf_lo(r.ldt)));
  const float a2 = bf_round(ex2(bf_lo(r.la) * 1.4426950408889634f)) * (dt * -1.4426950408889634f);
  const float f = bf_lo(r.ai) * dt;
  const float r128 = f * 20.371832715762604f;
  const uint32_t ex = min(max(__reduce_max_sync(0xffffffffu, max(r.cr & 0x7fffu, r.ci & 0x7fffu)) >> 7, 1u), 253u);
  const float cs = uf((254u - ex) << 23);
  sc = 2.f * dt * uf(ex << 23);
  const cpx C = {bf_lo(r.cr) * cs, -bf_lo(r.ci) * cs};
  auto put = [&](const __half2 (&v)[8], uint32_t off) {
    stsm4(ad.sa + off, hu(v[0]), hu(v[1]), hu(v[2]), hu(v[3]));
    stsm4(ad.sb + off, hu(v[4]), hu(v[5]), hu(v[6]), hu(v[7]));
  };
  uint32_t A[4][4], B[5][2][4];
  auto get = [&](int j, uint32_t off) {
    __syncwarp();
    ldsm4(B[j][0], ad.lb + off);
    ldsm4(B[j][1], ad.lc + 512 + off);
  };
  auto tile = [&](int j) {
    k[j][0] = k[j][1] = k[j][2] = k[j][3] = 0.f;
#pragma unroll
    for (int s = 0; s < 4; s++) mma_h(k[j], A[s], B[j][s >> 1][2 * (s & 1)], B[j][s >> 1][2 * (s & 1) + 1]);
  };
  auto after = [&](cpx v, uint32_t dep) { return cpx{uf(fu(v.r) ^ (dep & zero)), v.i}; };
  const cpx w1 = polar(a2, f), w128 = polar(a2 * 128.f, (r128 - rintf(r128)) * 6.283185307179586f);
  const cpx w2 = csq(w1), w4 = csq(w2);
  __half2 t0[8], t1[8], t2[8], t3[8], t4[8];
  const hmul m2 = mk_mul(w2), m4 = mk_mul(w4), m128 = mk_mul(w128);
  t0[0] = __floats2half2_rn(1.f, 0.f); t0[1] = __floats2half2_rn(w1.r, w1.i); t0[2] = m2.a; t0[4] = m4.a;
  t0[3] = hcm(t0[1], m2); t0[5] = hcm(t0[1], m4); t0[6] = hcm(t0[2], m4); t0[7] = hcm(t0[3], m4);
  put(t0, 0); get(0, 0);
  t1[0] = m128.a;
#pragma unroll
  for (int i = 1; i < 8; i++) t1[i] = hcm(t0[i], m128);
  put(t1, 1024); get(1, 1024);
  {
    cpx w8 = csq(after(w4, B[0][0][0]));
    w8.i = -w8.i;
    const cpx w16 = csq(w8), w32 = csq(w16), w64 = csq(w32);
    const hmul m8 = mk_mul(w8), m16 = mk_mul(w16), m32 = mk_mul(w32), m64 = mk_mul(w64);
    __half2 a[8];
    a[0] = __floats2half2_rn(C.r, C.i); a[1] = hcm(a[0], m8);
    a[2] = hcm(a[0], m16); a[3] = hcm(a[1], m16);
#pragma unroll
    for (int i = 0; i < 4; i++) a[4 + i] = hcm(a[i], m32);
    put(a, 0);
#pragma unroll
    for (int i = 0; i < 8; i++) a[i] = hcm(a[i], m64);
    put(a, 1024);
    __syncwarp();
#pragma unroll
    for (int s = 0; s < 4; s++) ldsm4(A[s], (ad.la ^ (s << 5)) + s * 256);
  }
  const cpx w256 = csq(after(w128, B[1][0][0]));
  const hmul m256 = mk_mul(w256);
  t2[0] = m256.a;
#pragma unroll
  for (int i = 1; i < 8; i++) t2[i] = hcm((i & 1) ? t1[i & 6] : t0[i & 6], m256);
  put(t2, 0); get(2, 0);
  tile(0); tile(1);
  const cpx w512 = csq(after(w256, A[0][0]));
  const hmul m512 = mk_mul(w512);
  t3[0] = m512.a;
#pragma unroll
  for (int i = 1; i < 8; i++) t3[i] = hcm((i & 2) ? t2[i & 5] : ((i & 1) ? t1[i & 4] : t0[i & 4]), m512);
  put(t3, 1024); get(3, 1024);
  tile(2);
  const cpx w1024 = csq(after(w512, B[2][0][0])), we = csq(w1024);
  const hmul m1024 = mk_mul(w1024);
  t4[0] = m1024.a;
#pragma unroll
  for (int i = 1; i < 8; i++) t4[i] = hcm((i & 4) ? t3[i & 3] : ((i & 2) ? t2[i & 1] : t1[0]), m1024);
  put(t4, 0); get(4, 0);
  tile(3); tile(4);
  k2048 = (C.r * we.r + C.i * we.i) * sc;
}

__device__ __forceinline__ void build_tables(uint32_t tb, int lane, float (&k)[5][4], float k2048) {
  const int g = lane >> 2, c = lane & 3;
  const uint32_t kc = tb + T_KC + 16;
  {
    const uint32_t a0 = kc + 16 * g + 4 * c, a2 = kc + 2 * (256 + 4 * g + c);
    const uint32_t a3 = kc + 2 * (384 + 2 * g + 64 * (c & 1) + (c >> 1)), a4 = kc + 2 * (512 + g + 32 * c);
#pragma unroll
    for (int r = 0; r < 2; r++) {
      sts32(a0 + 128 * r, pack_bf(k[0][2 * r], k[0][2 * r + 1]));
      sts32(a0 + 128 * r + 256, pack_bf(k[1][2 * r], k[1][2 * r + 1]));
      const uint32_t w2 = pack_bf(k[2][2 * r], k[2][2 * r + 1]);
      const uint32_t w3 = pack_bf(k[3][2 * r], k[3][2 * r + 1]);
      const uint32_t w4 = pack_bf(k[4][2 * r], k[4][2 * r + 1]);
      sts16(a2 + 64 * r, w2); sts16(a2 + 64 * r + 128, w2 >> 16);
      sts16(a3 + 32 * r, w3); sts16(a3 + 32 * r + 64, w3 >> 16);
      sts16(a4 + 16 * r, w4); sts16(a4 + 16 * r + 32, w4 >> 16);
    }
  }
  if (lane == 0) { sts16(kc + 2 * 640, pack_bf(k2048, 0.f)); sts16(kc - 2, 0); }
  __syncwarp();
  const uint32_t td = tb + T_D + 32;
  {
    const uint4 v = lds128(kc + 16 * lane);
    const uint32_t pv = lds16(kc + 16 * lane - 2);
    sts128(td + 32 * lane, __byte_perm(v.x, pv, 0x5410), __byte_perm(v.x, v.x, 0x1032), __byte_perm(v.y, v.x, 0x7610),
           __byte_perm(v.y, v.y, 0x1032));
    sts128(td + 32 * lane + 16, __byte_perm(v.z, v.y, 0x7610), __byte_perm(v.z, v.z, 0x1032),
           __byte_perm(v.w, v.z, 0x7610), __byte_perm(v.w, v.w, 0x1032));
  }
  {
    const uint2 v = lds64(kc + 512 + 8 * lane);
    const uint32_t k4 = lds16(kc + 512 + 8 * lane + 8);
    const uint32_t pv = lds16(kc + (lane == 0 ? 510 : 512 + 8 * lane));
    const uint32_t k22 = __byte_perm(v.y, v.y, 0x1010);
    sts128(td + 1024 + 32 * lane, __byte_perm(v.x, pv, 0x5410), __byte_perm(v.x, v.x, 0x1010),
           __byte_perm(v.x, v.x, 0x1032), __byte_perm(v.y, v.x, 0x7610));
    sts128(td + 1024 + 32 * lane + 16, k22, k22, __byte_perm(v.y, v.y, 0x1032), __byte_perm(k4, v.y, 0x7610));
  }
  {
    const uint32_t kk = lds16(kc + 2 * 384);
    const uint32_t w = lane < 3 ? (kk | (kk << 16)) : (lane == 3 ? (kk << 16) : 0u);
    if (lane < 24) sts32(td + 4 * (lane < 16 ? 512 + lane : lane - 24), w);
    const uint32_t lo_ = lds16(kc + 2 * 511), le_ = lds16(kc + 2 * 512);
    const uint32_t ja = tb + T_5 + (lane < 16 ? 4 * lane : 256 + 4 * lane);
    sts32(ja, lane == 16 ? (le_ << 16) : 0u);
    sts32(ja + 384, lane == 16 ? (lo_ << 16) : 0u);
    sts32(tb + (lane < 16 ? T_7 : T_9 - 64) + 4 * lane, 0u);
  }
#pragma unroll
  for (int s = 0; s < 2; s++) {
    const uint32_t b = kc + 2 * (s ? 512 : 384) + 8 * lane;
    const uint2 v = lds64(b);
    uint32_t em = lds16(b - 2), e0 = v.x;
    const uint32_t e4 = lds16(b + 8);
    if (lane == 0) { em = 0; e0 = 0; }
    sts64(tb + (s ? T_7 : T_3) + 64 + 8 * lane, __byte_perm(v.x, em, 0x5432), __byte_perm(v.y, v.x, 0x7632));
    sts64(tb + (s ? T_9 : T_5) + 64 + 8 * lane, __byte_perm(v.y, e0, 0x5410), __byte_perm(e4, v.y, 0x5410));
  }
  __syncwarp();
}

__device__ __forceinline__ uint32_t box2w(int lo, int n, int o) {
  return ((unsigned)(o - lo) < (unsigned)n ? 0x3F80u : 0u) | ((unsigned)(o + 1 - lo) < (unsigned)n ? 0x3F800000u : 0u);
}

#define SPLIT() asm volatile("{\n.reg .pred p;\nsetp.ne.u32 p, %0, 0;\n@p exit;\n}\n" ::"r"(blockIdx.y) : "memory")

__device__ __forceinline__ void conv_channel(uint32_t ub, uint32_t tb, int lane, uint4* ydst) {
  const int g = lane >> 2, c = lane & 3, x = g - 2 * c;
  const int mi = lane >> 3;
  const uint32_t qa = ub + U_PAD + 16 * (lane & 7) + ((mi == 0 || mi == 3) ? U_ODD : 0) - (mi == 0 ? 16 : 0);
  const uint32_t hb = ub + U_PAD + (mi & 1) * U_ODD + 16 * ((lane >> 4) + (lane & 7)) - 16;
  const uint32_t kv = lds16(tb + T_KC + 16 + 2 * 512);
  const int oh = c < 2 ? 8 + 2 * c : 2 * c - 8, og = c < 3 ? 2 * c : -10;
  uint32_t bx[4] = {box2w(g - 4, 9, 2 * c), box2w(g - 3, 7, 2 * c), box2w(g - 4, 9, oh), box2w(g - 3, 7, oh)};
  uint32_t by[4] = {box2w(g - 10, 5, 2 * c - 8), box2w(g - 5, 3, 2 * c - 8), box2w(g - 10, 5, og), box2w(g - 5, 3, og)};
  uint32_t lb0 = ((unsigned)(x + 5) < 2u ? kv : 0u) | ((unsigned)(x + 4) < 2u ? kv << 16 : 0u);
  uint32_t lb1 = ((unsigned)(x - 3) < 2u ? kv : 0u) | ((unsigned)(x - 4) < 2u ? kv << 16 : 0u);
  const int q0 = g - 1, q1 = c < 3 ? g : g - 2;
  uint32_t y0a = ub + U_PAD + (q0 & 1) * U_ODD + 16 * (q0 >> 1) + 4 * c;
  uint32_t y1a = ub + U_PAD + (q1 & 1) * U_ODD + 16 * (q1 >> 1) + 4 * c;
  uint32_t f3[3][4][4];
  {
    const uint32_t fa = tb + T_7 + 4 * (16 + x);
#pragma unroll
    for (int tt = 0; tt < 3; tt++)
#pragma unroll
      for (int D = 0; D < 4; D++) {
        const uint32_t a = fa + (tt == 0 ? 316 : (tt == 1 ? 320 : 0)) + 64 * D;
        f3[tt][D][0] = lds32(a); f3[tt][D][1] = lds32(a + 32); f3[tt][D][2] = lds32(a - 32); f3[tt][D][3] = lds32(a);
      }
  }
#pragma unroll
  for (int i = 0; i < 4; i++) asm volatile("" : "+r"(bx[i]), "+r"(by[i]));
  asm volatile("" : "+r"(lb0), "+r"(lb1), "+r"(y0a), "+r"(y1a));
  mbar_wait(BAR(MB_UFULL));
  mbar_wait(BAR(MB_EMPTY + 15));
  TS(36);
  float acc[16][4];
  {
    uint32_t z09[8], z07[8], zm9[8], zm7[8];
#pragma unroll
    for (int i = 0; i < 8; i++) {
      uint32_t h[4];
      ldsm4(h, hb + 128 * i);
      float y0, y1, y2, y3, w0, w1, w2, w3;
      mma0(y0, y1, y2, y3, bx[0], bx[1], bx[2], bx[3], h[2], c < 2 ? h[3] : h[1]);
      mma0(w0, w1, w2, w3, bx[0], bx[1], bx[2], bx[3], h[1], c < 2 ? h[2] : h[0]);
      z09[i] = pack_bf(y0, y1); z07[i] = pack_bf(y2, y3);
      zm9[i] = pack_bf(w0, w1); zm7[i] = pack_bf(w2, w3);
    }
    float a[4][2][4];
#pragma unroll
    for (int kap = 0; kap < 4; kap++)
#pragma unroll
      for (int sg = 0; sg < 2; sg++)
#pragma unroll
        for (int bk = 3; bk >= kap; bk--) {
          const uint32_t(&q0_)[4] = f3[sg ? 2 : 0][bk - kap];
          const uint32_t(&q1_)[4] = f3[sg ? 2 : 1][bk - kap];
          float(&a0)[4] = a[bk][0];
          float(&a1)[4] = a[bk][1];
          if (sg == 0 && kap == 0) {
            mma0(a0[0], a0[1], a0[2], a0[3], q0_[0], q0_[1], q0_[2], q0_[3], z09[0], z09[1]);
            mma0(a1[0], a1[1], a1[2], a1[3], q1_[0], q1_[1], q1_[2], q1_[3], zm9[0], zm9[1]);
          } else {
            mma(a0[0], a0[1], a0[2], a0[3], q0_[0], q0_[1], q0_[2], q0_[3], sg ? zm7[2 * kap] : z09[2 * kap], sg ? zm7[2 * kap + 1] : z09[2 * kap + 1]);
            mma(a1[0], a1[1], a1[2], a1[3], q1_[0], q1_[1], q1_[2], q1_[3], sg ? z07[2 * kap] : zm9[2 * kap], sg ? z07[2 * kap + 1] : zm9[2 * kap + 1]);
          }
        }
    SPLIT();
#pragma unroll
    for (int i = 0; i < 8; i++) {
      uint32_t h[4];
      ldsm4(h, qa + 128 * i);
      const float ci[4] = {a[i >> 1][0][2 * (i & 1)], a[i >> 1][0][2 * (i & 1) + 1], a[i >> 1][1][2 * (i & 1)], a[i >> 1][1][2 * (i & 1) + 1]};
      mmac(acc[8 + i], h[0], h[1], h[2], h[3], lb0, lb1, ci);
    }
  }
  TS(44);
  {
    uint2 a5[10], a3[10];
    const uint32_t aa = tb + T_5 + 4 * (8 + 2 * g - 2 * c);
#pragma unroll
    for (int m = 0; m < 10; m++) { a5[m] = lds64(aa + 32 * m); a3[m] = lds64(aa + 384 + 32 * m); }
    uint32_t x5[12][2], x3[12][2];
    auto ygen = [&](int kap) {
#pragma unroll
      for (int hh = 0; hh < 2; hh++) {
        float y0, y1, y2, y3;
        mma0(y0, y1, y2, y3, by[0], by[1], by[2], by[3], lds32(y0a + 128 * kap + 64 * hh), lds32(y1a + 128 * kap + 64 * hh));
        x5[kap][hh] = pack_bf(y0, y1);
        x3[kap][hh] = pack_bf(y2, y3);
      }
    };
    ygen(11); ygen(10); ygen(9); ygen(8);
#pragma unroll
    for (int kap = 11; kap >= 0; kap--) {
      if (kap >= 4) ygen(kap - 4);
#pragma unroll
      for (int sg = 0; sg < 2; sg++)
#pragma unroll
        for (int i = 4; i >= 0; i--) {
          const int be = kap + 4 + i;
          if (be <= 15) {
            const uint2 &hi = sg ? a3[2 * i + 1] : a5[2 * i + 1], &lo = sg ? a3[2 * i] : a5[2 * i];
            const uint32_t b0 = sg ? x3[kap][0] : x5[kap][0], b1 = sg ? x3[kap][1] : x5[kap][1];
            if (be < 8 && i == 0 && sg == 0) mma0(acc[be][0], acc[be][1], acc[be][2], acc[be][3], hi.x, hi.y, lo.x, lo.y, b0, b1);
            else mma(acc[be][0], acc[be][1], acc[be][2], acc[be][3], hi.x, hi.y, lo.x, lo.y, b0, b1);
          }
        }
    }
  }
  TS(45);
  {
    const uint32_t st = tb + T_ST + lane * 8;
#pragma unroll
    for (int be = 4; be < 12; be++) sts64(st + 256 * be, pack_bf(acc[be][0], acc[be][1]), pack_bf(acc[be][2], acc[be][3]));
    SPLIT();
    uint32_t F[66], qd[8][4];
    const uint32_t fa = tb + T_D + 32 + 4 * x;
#pragma unroll
    for (int i = 0; i < 32; i++) {
      const int s = 120 - (i >> 2) - 8 * (i & 3);
      uint32_t(&q)[4] = qd[i & 7];
      ldsm4(q, qa + 16 * s);
      const int m = 16 * (i & 3) + 2 * (i >> 2);
      F[m] = lds32(fa + 32 * m); F[m + 1] = lds32(fa + 32 * m + 32);
#pragma unroll
      for (int be = 15; be >= 12; be--) {
        const int de = 8 * be - s;
        if (de >= 0) mma(acc[be][0], acc[be][1], acc[be][2], acc[be][3], q[0], q[1], q[2], q[3], F[2 * de + 1], F[2 * de]);
      }
    }
    F[64] = lds32(fa + 32 * 64); F[65] = lds32(fa + 32 * 65);
    uint32_t qp = qa + 128 * 11, sta = st + 256 * 10;
    uint4* yd = ydst + 7 * 32;
#pragma unroll
    for (int i = 0; i < 6; i++) ldsm4(qd[i], qp - 16 * i);
    uint2 sv = lds64(sta + 256);
    float ci[4] = {bf_lo(sv.x), bf_hi(sv.x), bf_lo(sv.y), bf_hi(sv.y)};
    float T[5][4];
#pragma unroll
    for (int i = 0; i < 16; i++) T[i >> 2][i & 3] = acc[12 + (i >> 2)][i & 3];
    nb_sync(NB_YZ, 160);
    TS(46);
#pragma unroll 1
    for (int bp = 5; bp >= 0; bp--) {
      uint32_t held[2];
#pragma unroll
      for (int o = 1; o >= 0; o--) {
#pragma unroll
        for (int k = 4; k >= 1; k--) mmac(T[k], qd[0][0], qd[0][1], qd[0][2], qd[0][3], F[16 * k + 1], F[16 * k], T[k - 1]);
        mmac(T[0], qd[0][0], qd[0][1], qd[0][2], qd[0][3], F[1], F[0], ci);
        ldsm4(qd[6], qp - 16 * 6);
        ldsm4(qd[7], qp - 16 * 7);
        sv = lds64(sta);
#pragma unroll
        for (int i = 1; i < 8; i++) {
#pragma unroll
          for (int k = 3; k >= 0; k--)
            mma(T[k][0], T[k][1], T[k][2], T[k][3], qd[i][0], qd[i][1], qd[i][2], qd[i][3], F[16 * k + 2 * i + 1], F[16 * k + 2 * i]);
          if (i < 7) ldsm4(qd[i - 1], qp - 128 - 16 * (i - 1));
          if (i == 2) {
            const uint32_t w0 = pack_bf(T[4][0], T[4][1]), w1 = pack_bf(T[4][2], T[4][3]);
            if (o) { held[0] = w0; held[1] = w1; }
            else st_x(yd, nz(w0), w1, held[0], held[1]);
          }
          if (i == 4) {
            if (2 * bp + o <= 4) sv = make_uint2(0, 0);
            ci[0] = bf_lo(sv.x); ci[1] = bf_hi(sv.x); ci[2] = bf_lo(sv.y); ci[3] = bf_hi(sv.y);
          }
        }
        qp -= 128; sta -= 256;
      }
      yd -= 32;
    }
#pragma unroll
    for (int B = 1; B >= 0; B--)
      st_x(ydst + B * 32, nz(pack_bf(T[2 * B][0], T[2 * B][1])), pack_bf(T[2 * B][2], T[2 * B][3]),
           pack_bf(T[2 * B + 1][0], T[2 * B + 1][1]), pack_bf(T[2 * B + 1][2], T[2 * B + 1][3]));
  }
}

__device__ __forceinline__ void dual_exp(const uint32_t* w, uint32_t* e) {
  const float L = 1.44268798828125f;
  uint32_t mx = bmax2(bmax2(w[0], w[1]), bmax2(w[2], w[3]));
  uint32_t mn = bmin2(bmin2(w[0], w[1]), bmin2(w[2], w[3]));
  mx = bmax2(mx, __shfl_xor_sync(0xffffffffu, mx, 1));
  mn = bmin2(mn, __shfl_xor_sync(0xffffffffu, mn, 1));
  mx = bmax2(mx, __shfl_xor_sync(0xffffffffu, mx, 2));
  mn = bmin2(mn, __shfl_xor_sync(0xffffffffu, mn, 2));
  const float mx0 = bf_lo(mx) * -L, mx1 = bf_hi(mx) * -L, mn0 = bf_lo(mn) * L, mn1 = bf_hi(mn) * L;
#pragma unroll
  for (int i = 0; i < 2; i++) {
    const float a0 = bf_lo(w[2 * i]), a1 = bf_hi(w[2 * i]), b0 = bf_lo(w[2 * i + 1]), b1 = bf_hi(w[2 * i + 1]);
    e[2 * i] = pack_bf(ex2(fmaf(a0, L, mx0)), ex2(fmaf(b0, L, mx0)));
    e[2 * i + 1] = pack_bf(ex2(fmaf(a1, L, mx1)), ex2(fmaf(b1, L, mx1)));
    e[4 + 2 * i] = pack_bf(ex2(fmaf(a0, -L, mn0)), ex2(fmaf(b0, -L, mn0)));
    e[5 + 2 * i] = pack_bf(ex2(fmaf(a1, -L, mn1)), ex2(fmaf(b1, -L, mn1)));
  }
}
__device__ __forceinline__ void norm_store(const uint32_t* e, uint32_t dst) {
  float s[4];
  mma0(s[0], s[1], s[2], s[3], e[0], e[1], e[2], e[3], 0x3F803F80u, 0x3F803F80u);
  const uint32_t r = pack_bf(rcp(s[0]), rcp(s[2]));
  const __nv_bfloat162 rr = *(const __nv_bfloat162*)&r;
  uint32_t o[4];
#pragma unroll
  for (int i = 0; i < 4; i++) {
    const __nv_bfloat162 v = __hmul2(*(const __nv_bfloat162*)&e[i], (i & 1) ? __high2bfloat162(rr) : __low2bfloat162(rr));
    o[i] = *(const uint32_t*)&v;
  }
  stsm4(dst, o[0], o[1], o[2], o[3]);
}

__global__ void __launch_bounds__(NTHREADS, 1)
fused_kernel(const Params P, const __grid_constant__ CUtensorMap mx, const __grid_constant__ CUtensorMap mw,
             const __grid_constant__ CUtensorMap mo, const __grid_constant__ CUtensorMap mu,
             const __grid_constant__ CUtensorMap mout, const __grid_constant__ CUtensorMap mw4) {
  constexpr uint32_t sb = SB;
  const int tid = threadIdx.x, lane = tid & 31;
  const int warp = __shfl_sync(0xffffffffu, tid >> 5, 0);
  const int b = blockIdx.x, oct = b >> 3, i8 = b & 7;
  const int rt = oct < 8 ? oct : 15 - oct;
  const int hp = (oct >> 3) * 8 + i8;

  const int wg = warp >> 2, w = warp & 3;
  const int d = b * 4 + ((tid >> 5) & 3);
  if (tid < 384) {
    asm volatile("prefetch.tensormap [%0];" ::"l"(&mu) : "memory");
    asm volatile("prefetch.tensormap [%0];" ::"l"(&mw) : "memory");
    asm volatile("prefetch.tensormap [%0];" ::"l"(&mx) : "memory");
    asm volatile("prefetch.tensormap [%0];" ::"l"(&mw4) : "memory");
  }
  if (warp == 12) {
    if (lane == 0) {
#pragma unroll
      for (int i = 0; i < 9; i++) mbar_init(BAR(i), 1);
      asm volatile("fence.mbarrier_init.release.cluster;" ::: "memory");
    }
    __syncwarp();
    if (lane < 9) mbar_expect(BAR(0) + 8 * lane, lane == 5 ? 65536 : ((lane == 0 || lane > 5) ? 16384 : 28672));
    __syncwarp();
    e_tma3d(sb + OFF_W, &mw, BAR(MB_FULL), hp * 32, 0, 0);
    e_tma2d(sb + OFF_X + 3 * 16384, &mx, BAR(MB_FULL), 0, rt * 256);
  } else if (warp == 13) {
    if (lane == 0) {
#pragma unroll
      for (int i = 9; i < 39; i++) mbar_init(BAR(i), i < MB_EMPTY ? 1 : (i < MB_AUX ? 4 : 9));
      asm volatile("fence.mbarrier_init.release.cluster;" ::: "memory");
    }
    __syncwarp();
    if (lane < 9) mbar_expect(BAR(MB_FULL + 8) + 8 * lane, lane < 8 ? 16384 : 131072);
  }
  const KgenRaw raw = kgen_load(P, d, tid >> 7, lane);
  const unsigned short dsk = __ldg((const unsigned short*)P.Dskip + d);
  const uint32_t tb = sb + OFF_T + w * T_CH;
  const uint32_t kp = wg >= 2 ? sb + OFF_STG0 + 16384 + w * 2048 : ((tb + 127) & ~127u) + wg * 2048;
  const KgenAddr kad = kgen_addr(lane, wg == 3 ? sb + OFF_X + 32768 + w * 2048 : kp);
  if (warp == 12) {
#pragma unroll 1
    for (int kb = 1; kb < 4; kb++) {
      if (kb == U_AT) e_tma5d(sb + OFF_STG0, &mu, BAR(MB_URAW), i8 * 64, oct * 4);
      e_tma3d(sb + OFF_W + kb * 12288, &mw, BAR(MB_FULL) + 8 * kb, hp * 32, kb * 64, 0);
      e_tma2d(sb + OFF_X + (kb < 2 ? kb + 3 : kb - 2) * 16384, &mx, BAR(MB_FULL) + 8 * kb, kb * 64, rt * 256);
    }
    e_prefetch(P.x + (size_t)(rt * 256 + hp * 16) * 512, 16384);
    e_tma4d(sb + OFF_W + 4 * 12288, &mw4, BAR(MB_FULL + 4), hp * 32, 4);
    if (smem_u32(smem_raw) != SB) __trap();
    if (lane == 0) TS1(54);
  }
  float k[5][4], k2048, ksc;
  kgen_unit(raw, kad, blockIdx.y, k, k2048, ksc);
  TS(40 + wg);
  if ((fu(k[0][0]) & fu(k[1][0]) & fu(k[2][0]) & fu(k[3][0]) & fu(k[4][0])) == 0xffffffffu) sts32(kp, 0);
  if (wg == 3) {
    nb_sync(0, 512);
    if (warp == 12) {
      asm volatile("fence.proxy.async.shared::cta;" ::: "memory");
      e_tma2d(sb + OFF_X + 2 * 16384, &mx, BAR(MB_FULL + 4), 256, rt * 256);
    }
  } else if (wg) {
    nb_arrive(0, 512);
  }
  k2048 += __shfl_xor_sync(0xffffffffu, k2048, 16);
  k2048 += __shfl_xor_sync(0xffffffffu, k2048, 8);
  if (wg != 2) {
    uint32_t h[10];
#pragma unroll
    for (int j = 0; j < 10; j++) h[j] = hu(__floats2half2_rn(k[j >> 1][2 * (j & 1)], k[j >> 1][2 * (j & 1) + 1]));
    sts128(kp + lane * 16, h[0], h[1], h[2], h[3]);
    sts128(kp + 512 + lane * 16, h[4], h[5], h[6], h[7]);
    sts128(kp + 1024 + lane * 16, h[8], h[9], fu(k2048), fu(ksc));
  }
  if (wg == 0) { nb_arrive(NB_PREP, 512); nb_sync(0, 512); }
  else if (wg == 3) nb_arrive(NB_PREP, 512);
  else nb_sync(NB_PREP, 512);
  if (warp >= 12) {
    asm volatile("setmaxnreg.dec.sync.aligned.u32 32;");
    if (warp == 12) {
      uint32_t slot = sb + OFF_X + 3 * 16384;
#pragma unroll 1
      for (int n = 0; n < 11; n++) {
        mbar_spin(BAR(MB_EMPTY) + 8 * n);
        const int m = n + 5;
        e_tma2d(slot, &mx, BAR(MB_FULL) + 8 * m, (m & 7) * 64, rt * 256 + (m >> 3) * 128);
        slot = slot == sb + OFF_X + 4 * 16384 ? sb + OFF_X : slot + 16384;
        if (n == 7) e_prefetch(P.wo + (size_t)b * 2048, 4096);
      }
#pragma unroll 1
      for (int i = 0; i < 8; i++) {
        mbar_wait(BAR(MB_EMPTY + 10) + 8 * ((0x54332100u >> (4 * i)) & 7));
        const int w0 = (0x54736210u >> (4 * i)) & 7;
        e_tma3d(sb + OFF_W + w0 * 16384, &mo, BAR(MB_WO), 0, w0 * 64, (hp & 3) * 2);
      }
    } else {
      if (warp == 15) {
        const uint4 v0 = __ldg((const uint4*)P.wphi + hp * 64 + lane), v1 = __ldg((const uint4*)P.wphi + hp * 64 + 32 + lane);
        sts128(sb + OFF_PHI + (lane & 1) * 256 + (lane >> 1) * 16, v0.x, v0.y, v0.z, v0.w);
        sts128(sb + OFF_PHI + 512 + (lane & 1) * 256 + (lane >> 1) * 16, v1.x, v1.y, v1.z, v1.w);
        asm volatile("fence.proxy.async.shared::cta;" ::: "memory");
        __syncwarp();
        if (lane == 0) mbar_arrive(BAR(MB_AUX));
        mbar_wait(BAR(MB_EMPTY + ZERO_STEP));
        uint4* py = P.xs + X_Y + b * 1024 + lane;
#pragma unroll 1
        for (int i = 0; i < 1024; i += 32) st_x(py + i, 0, 0, 0, 0);
        nb_arrive(NB_YZ, 160);
        nb_arrive(NB_ODONE, 320);
        if (lane == 0) TS1(55);
        return;
      }
      uint32_t* const cnt = (uint32_t*)(P.xs + X_CNT) + (warp == 13 ? i8 : 8 + rt) * 32;
      const unsigned target = (ld_x32(cnt) & ~15u) + 16;
      if (warp == 13) {
        uint4* pp = P.xs + X_PART + (hp * 8 + rt) * 144 + lane;
#pragma unroll 1
        for (int i = 0; i < 144; i += 32) if (i + lane < 144) st_x(pp + i, 0, 0, 0, 0);
      }
      nb_sync(warp == 13 ? NB_INIT : NB_ODONE, warp == 13 ? 160 : 320);
      if (lane == 0) TS1(warp == 13 ? 49 : 56);
      asm volatile("fence.proxy.async.shared::cta;" ::: "memory");
      if (lane == 0) asm volatile("red.release.gpu.global.add.u32 [%0], 1;" ::"l"(cnt) : "memory");
      if (lane == 0) TS1(warp == 13 ? 50 : 57);
      const uint32_t* pc = (warp == 13 && (lane & 1)) ? (uint32_t*)(P.xs + X_CNT) + (b >> 4) * 32 : cnt;
#pragma unroll 1
      for (int i = 0; i < SPIN_MAX; i++) {
        unsigned v;
        asm volatile("ld.acquire.gpu.global.u32 %0, [%1];" : "=r"(v) : "l"(pc) : "memory");
        if (__all_sync(0xffffffffu, (int)(v - target) >= 0)) break;
      }
      if (lane == 0) TS1(warp == 13 ? 51 : 58);
      asm volatile("fence.proxy.async.global;" ::: "memory");
      if (warp == 13) {
        mbar_wait(BAR(MB_EMPTY + 11));
        e_expect(BAR(MB_UFULL), 4 * U_CH);
        e_bulk(sb + OFF_U, P.xs + X_UT + b * (U_CH / 4), 4 * U_CH, BAR(MB_UFULL));
      } else {
        const uint4* src = P.xs + X_O + (rt * 4 + (hp >> 2)) * 4096;
        e_expect(BAR(MB_OA), 14336);
        e_bulk(sb + OFF_STG0, src + 3200, 14336, BAR(MB_OA));
        e_expect(BAR(MB_OC), 32768);
        e_bulk(sb + OFF_X + 32768, src, 32768, BAR(MB_OC));
        nb_sync(NB_BDONE, 288);
        asm volatile("fence.proxy.async.shared::cta;" ::: "memory");
        e_expect(BAR(MB_OB), 18432);
        e_bulk(sb + OFF_U, src + 2048, 18432, BAR(MB_OB));
      }
    }
    return;
  }

  const int t = tid & 127;
  const int g = lane >> 2, c = lane & 3;
  {
    if (wg == 2) {
      asm volatile("setmaxnreg.inc.sync.aligned.u32 160;");
#pragma unroll
      for (int j = 0; j < 5; j++) { k[j][0] *= ksc; k[j][1] *= ksc; k[j][2] *= ksc; k[j][3] *= ksc; }
#pragma unroll 1
      for (int q = 0; q < 3; q++) {
        const uint32_t src = (q == 2 ? kp : ((tb + 127) & ~127u) + q * 2048) + lane * 16;
        const uint4 v0 = lds128(src), v1 = lds128(src + 512), v2 = lds128(src + 1024);
        const uint32_t h[10] = {v0.x, v0.y, v0.z, v0.w, v1.x, v1.y, v1.z, v1.w, v2.x, v2.y};
#pragma unroll
        for (int j = 0; j < 10; j++) {
          const float2 f = __half22float2(*(const __half2*)&h[j]);
          k[j >> 1][2 * (j & 1)] = fmaf(f.x, uf(v2.w), k[j >> 1][2 * (j & 1)]);
          k[j >> 1][2 * (j & 1) + 1] = fmaf(f.y, uf(v2.w), k[j >> 1][2 * (j & 1) + 1]);
        }
        k2048 += uf(v2.z);
      }
#pragma unroll
      for (int o2 = 4; o2; o2 >>= 1) k2048 += __shfl_xor_sync(0xffffffffu, k2048, o2);
      if (lane == 0) k[0][0] += bf_lo(dsk);
      __syncwarp();
      if (lane == 0) mbar_arrive(BAR(MB_AUX));
      TS(34);
      build_tables(tb, lane, k, k2048);
      TS(35);
      uint4* const g_y = P.xs + X_Y;
      conv_channel(sb + OFF_U + w * U_CH, tb, lane, g_y + (size_t)d * 256 + lane);
      nb_arrive(NB_BDONE, 288);
      TS(37);
      mbar_wait(BAR(MB_OA));
      const int lam = w * 8 + g;
      const uint4* src = g_y + (size_t)(oct * 32 + c * 8) * 256 + i8 * 32 + lam;
      uint4 v[8];
#pragma unroll 1
      for (int it = 0; it < SPIN_MAX; it++) {
        uint32_t m = 0xffffffffu;
#pragma unroll
        for (int i = 0; i < 8; i++) v[i] = ld_x(src + i * 256);
#pragma unroll
        for (int i = 0; i < 8; i++) m = min(m, v[i].x);
        if (__all_sync(0xffffffffu, m != 0)) break;
      }
      __nv_bfloat16* dst = P.out + (size_t)(i8 * 256 + (lam >> 2) * 16 + (lam & 3) * 2) * 1024 + 512 + oct * 32 + c * 8;
#pragma unroll
      for (int i = 0; i < 8; i++) *(uint4*)(dst + (size_t)((i >> 2) * 128 + ((i >> 1) & 1) * 8 + (i & 1)) * 1024) = tr_row(v, i);
      TS(38);
      GT(63);
      if (w == 0) TSDUMP(32);
      return;
    }
    if (wg == 1) {
      mbar_wait(BAR(MB_URAW));
      TS(48);
      uint4* dst = P.xs + X_UT + (i8 * 64 + g) * (U_CH / 16) + (c & 1) * (U_ODD / 16) + U_PAD / 16 + oct * 8 + w * 2 + (c >> 1);
      uint32_t r[8][4];
#pragma unroll
      for (int i = 0; i < 8; i++) ldsm4t(r[i], sb + OFF_STG0 + w * 4096 + lane * 128 + (((i ^ lane) & 7) << 4));
#pragma unroll
      for (int i = 0; i < 8; i++) dst[i * (U_CH / 2)] = make_uint4(r[i][0], r[i][1], r[i][2], r[i][3]);
      nb_arrive(NB_INIT, 160);
      if (lane == 0) mbar_arrive(BAR(MB_AUX));
      mbar_wait(BAR(MB_EMPTY + 4));
      mbar_spin(BAR(MB_EMPTY + 6));
    }
    TS(wg * 16 + 1);
  }

  float acc[2][48];
  {
    uint32_t fb = BAR(MB_FULL) + 64 * wg;
    uint32_t da = (uint32_t)mkdesc(sb + OFF_X, 16, 0, 0) + (wg ? 1024 : 3072), db = (uint32_t)mkdesc(sb + OFF_W, 4096, 0, 0);
    constexpr uint64_t ha = mkdesc(0, 0, 1024, 1), hb = mkdesc(0, 0, 512, 2);
#pragma unroll 1
    for (int kb = 0; kb < 8; kb++) {
      mbar_spin(fb);
      if (kb == 0) TS(wg * 16 + 2);
      WG_FENCE();
#pragma unroll
      for (int k = 0; k < 4; k++) {
        wgmma_ss_n96(acc[0], ha | (da + 2 * k), hb | (db + 64 * k), k ? 1 : kb);
        wgmma_ss_n96(acc[1], ha | (da + 2 * k + 512), hb | (db + 64 * k), k ? 1 : kb);
      }
      WG_COMMIT();
      WG_WAIT(1);
      if (kb > 0 && lane == 0) mbar_arrive(fb + 8 * (MB_EMPTY - MB_FULL - 1));
      fb += 8; db += 768;
      da = da == (uint32_t)mkdesc(sb + OFF_X + 65536, 16, 0, 0) ? da - 4096 : da + 1024;
    }
    WG_WAIT(0);
    if (lane == 0) mbar_arrive(fb + 8 * (MB_EMPTY - MB_FULL - 1));
    mbar_spin(fb + 8 * (MB_EMPTY - MB_FULL - 1));
  }
  TS(wg * 16 + 3);
  asm volatile("setmaxnreg.inc.sync.aligned.u32 160;");

  constexpr uint32_t stg0 = sb + OFF_STG0, stg1 = sb + OFF_X + 32768;
  const uint32_t sl = (wg ? stg1 : stg0) + w * 3072 + lane * 16;
  uint32_t pw[32], eq[32], vp[16];
  {
    uint4 af[8];
#pragma unroll
    for (int u = 0; u < 8; u++) {
      const float* a = acc[(u >> 1) & 1] + (u < 4 ? 16 : 0) + 8 * (u & 1);
      af[u] = make_uint4(pack_bf(a[0], a[1]), pack_bf(a[2], a[3]), pack_bf(a[4], a[5]), pack_bf(a[6], a[7]));
    }
    mbar_wait(BAR(MB_AUX));
    float p[8][8];
    WG_FENCE();
#pragma unroll
    for (int u = 0; u < 8; u++) wgmma_rs_n16(p[u], af[u], mkdesc(sb + OFF_PHI + (u & 1) * 512, 128, 256, 0), 0);
    WG_COMMIT();
#pragma unroll
    for (int i = 0; i < 16; i++) vp[i] = pack_bf(acc[i >> 3][32 + 2 * (i & 7)], acc[i >> 3][33 + 2 * (i & 7)]);
    WG_WAIT(0);
#pragma unroll
    for (int u = 0; u < 8; u++) {
      pw[4 * u] = pack_bf(p[u][0], p[u][2]); pw[4 * u + 1] = pack_bf(p[u][1], p[u][3]);
      pw[4 * u + 2] = pack_bf(p[u][4], p[u][6]); pw[4 * u + 3] = pack_bf(p[u][5], p[u][7]);
    }
  }
  uint4* const g_part = P.xs + X_PART;
  uint4* const g_o = P.xs + X_O;
  constexpr uint32_t kvs = stg0;
#pragma unroll 1
  for (int it = 0; it < 2; it++) {
#pragma unroll
    for (int u = 0; u < 4; u++) dual_exp(pw + 4 * u, eq + 8 * u);
    if (it == 0) {
      TS(wg * 16 + 12);
      mbar_wait(BAR(MB_EMPTY + 15));
#pragma unroll
      for (int i = 0; i < 4; i++) stsm4(sl + (i >> 1) * 12288 + 2048 + (i & 1) * 512, vp[4 * i], vp[4 * i + 1], vp[4 * i + 2], vp[4 * i + 3]);
#pragma unroll
      for (int i = 0; i < 8; i++) norm_store(eq + 4 * i, sl + (i >> 2) * 12288 + (i & 3) * 512);
      if (wg) {
        nb_arrive(NB_ST0, 256);
      } else {
        nb_sync(NB_WG0, 128);
        mbar_wait(BAR(MB_UFULL));
        float kv[12], kw[12];
#pragma unroll
        for (int i = 0; i < 12; i++) kv[i] = kw[i] = 0.f;
        const int mi = lane >> 3;
        const uint32_t ao = w * 512 + (lane & 7) * 16 + ((mi & 1) * 2 + (mi >> 1)) * 128, bo = 2048 + (w >> 1) * 512 + lane * 16;
#pragma unroll 1
        for (int j = 0; j < 2; j++) {
          if (j) nb_sync(NB_ST0, 256);
          const uint32_t sg = j ? stg1 : stg0;
          uint32_t a[8][4], bb[8][4];
#pragma unroll
          for (int s = 0; s < 8; s++) { ldsm4t(a[s], sg + s * 3072 + ao); ldsm4t(bb[s], sg + s * 3072 + bo); }
#pragma unroll
          for (int s = 0; s < 8; s++) {
            float* o = (s & 1) ? kw : kv;
            mma(o[0], o[1], o[2], o[3], a[s][0], a[s][1], a[s][2], a[s][3], bb[s][0], bb[s][1]);
            mma(o[4], o[5], o[6], o[7], a[s][0], a[s][1], a[s][2], a[s][3], bb[s][2], bb[s][3]);
            mma(o[8], o[9], o[10], o[11], a[s][0], a[s][1], a[s][2], a[s][3], 0x3F803F80u, 0x3F803F80u);
          }
        }
#pragma unroll
        for (int i = 0; i < 12; i++) kv[i] += kw[i];
        uint4* pp = g_part + (size_t)(hp * 8 + rt) * 144;
        st_x(pp + t, nz(pack_bf(kv[0], kv[1])), pack_bf(kv[2], kv[3]), pack_bf(kv[4], kv[5]), pack_bf(kv[6], kv[7]));
        if (c < 2) st_x32((uint32_t*)(pp + 128) + w * 16 + c * 8 + g, nz(fu(c ? kv[10] : kv[8])));
        TS(5);
      }
#pragma unroll
      for (int i = 0; i < 16; i++) pw[i] = pw[i + 16];
    }
  }
  TS(wg * 16 + 4);
  if (wg == 0) {
    const uint4* ps = g_part + (size_t)hp * 8 * 144 + t;
    const uint32_t* zs = (const uint32_t*)(g_part + (size_t)(hp * 8 + (lane >> 4) * 4) * 144 + 128) + w * 16 + (lane & 15);
    uint4 v[8];
    uint32_t zv[4];
#pragma unroll 1
    for (int it = 0; it < SPIN_MAX; it++) {
#pragma unroll
      for (int i = 0; i < 8; i++) v[i] = ld_x(ps + i * 144);
#pragma unroll
      for (int i = 0; i < 4; i++) zv[i] = ld_x32(zs + i * 576);
      uint32_t m = min(min(zv[0], zv[1]), min(zv[2], zv[3]));
#pragma unroll
      for (int i = 0; i < 8; i++) m = min(m, v[i].x);
      if (__all_sync(0xffffffffu, m != 0)) break;
    }
    float s4[4][4];
#pragma unroll
    for (int i = 0; i < 4; i++) s4[i][0] = s4[i][1] = s4[i][2] = s4[i][3] = 0.f;
    const uint32_t eye = (g >> 1) == c ? ((g & 1) ? 0x3F800000u : 0x3F80u) : 0u;
#pragma unroll
    for (int r = 0; r < 8; r++) {
      mma_k8(s4[(r & 1) * 2], v[r].x, v[r].y, eye);
      mma_k8(s4[(r & 1) * 2 + 1], v[r].z, v[r].w, eye);
    }
    float s[8];
#pragma unroll
    for (int i = 0; i < 8; i++) s[i] = s4[i >> 2][i & 3] + s4[2 + (i >> 2)][i & 3];
    float zsum = (uf(zv[0]) + uf(zv[1])) + (uf(zv[2]) + uf(zv[3]));
    zsum += __shfl_xor_sync(0xffffffffu, zsum, 16);
    stsm4(kvs + w * 512 + lane * 16, pack_bf(s[0], s[1]), pack_bf(s[2], s[3]), pack_bf(s[4], s[5]), pack_bf(s[6], s[7]));
    sts16(kvs + 2048 + (lane >> 4) * 128 + (w * 16 + (lane & 15)) * 2, lane < 16 ? pack_bf(zsum, 0.f) : 0x3F80u);
    TS(6);
  }
  nb_sync(NB_KV, 256);
  {
    uint32_t kb_[4][4], zb[8];
#pragma unroll
    for (int i = 0; i < 4; i++) ldsm4t(kb_[i], kvs + i * 512 + lane * 16);
#pragma unroll
    for (int i = 0; i < 8; i++) zb[i] = lds32(kvs + 2048 + (g & 1) * 128 + i * 16 + c * 4);
    uint32_t* od = (uint32_t*)(g_o + (size_t)((rt * 4 + wg * 2) * 32 + hp * 2) * 128) + w * 64 + lane;
#pragma unroll
    for (int mt = 0; mt < 2; mt++) {
#pragma unroll
      for (int h = 0; h < 2; h++) {
        const uint32_t* e = eq + 16 * mt + 8 * h;
        float n[8], nm[8], dp[4], dm[4];
        mma0(dp[0], dp[1], dp[2], dp[3], e[0], e[1], e[2], e[3], zb[4 * h], zb[4 * h + 1]);
        mma0(dm[0], dm[1], dm[2], dm[3], e[4], e[5], e[6], e[7], zb[4 * h + 2], zb[4 * h + 3]);
        mma0(n[0], n[1], n[2], n[3], e[0], e[1], e[2], e[3], kb_[2 * h][0], kb_[2 * h][1]);
        mma0(nm[0], nm[1], nm[2], nm[3], e[4], e[5], e[6], e[7], kb_[2 * h + 1][0], kb_[2 * h + 1][1]);
        mma0(n[4], n[5], n[6], n[7], e[0], e[1], e[2], e[3], kb_[2 * h][2], kb_[2 * h][3]);
        mma0(nm[4], nm[5], nm[6], nm[7], e[4], e[5], e[6], e[7], kb_[2 * h + 1][2], kb_[2 * h + 1][3]);
        const float q0 = dp[1] * rcp(dm[1]), q1 = dp[3] * rcp(dm[3]);
        const float r0 = rcp(fmaf(dm[0], q0, fmaf(dp[1], 1e-6f, dp[0]))), r1 = rcp(fmaf(dm[2], q1, fmaf(dp[3], 1e-6f, dp[2])));
#pragma unroll
        for (int i = 0; i < 8; i++) n[i] = fmaf(nm[i], (i & 2) ? q1 : q0, n[i]);
        od[h * 512] = pack_bf(n[0] * r0, n[1] * r0);
        od[h * 512 + 32] = pack_bf(n[2] * r1, n[3] * r1);
        od[h * 512 + 256] = pack_bf(n[4] * r0, n[5] * r0);
        od[h * 512 + 288] = pack_bf(n[6] * r1, n[7] * r1);
      }
      od += 16384;
    }
  }
  TS(wg * 16 + 7);
  nb_arrive(NB_ODONE, 320);
  if (wg) { if (w == 0) TSDUMP(16); return; }
  mbar_wait(BAR(MB_WO));
  mbar_wait(BAR(MB_OA));
  TS(8);
  nb_sync(NB_BDONE, 288);
  TS(9);
  float oc[64];
  {
    constexpr uint64_t ha = mkdesc(0, 0, 128, 0), hb = mkdesc(0, 0, 1024, 1);
    constexpr uint32_t da0 = (uint32_t)mkdesc(stg1, 1024, 0, 0), db0 = (uint32_t)mkdesc(sb + OFF_W, 8192, 0, 0);
#pragma unroll 1
    for (int j = 0; j < 8; j++) {
      const int kb = (j + 7) & 7;
      if ((j & 3) == 1) mbar_spin(j == 1 ? BAR(MB_OC) : BAR(MB_OB));
      WG_FENCE();
#pragma unroll
      for (int k = 0; k < 4; k++) wgmma_ss_n128(oc, ha | (da0 + 512 * kb + 128 * k), hb | (db0 + 1024 * kb + 128 * k), k ? 1 : j);
      WG_COMMIT();
    }
    WG_WAIT(0);
  }
  TS(10);
  nb_sync(NB_WG0, 128);
  const uint32_t ot = sb + OFF_W + w * 4096;
#pragma unroll
  for (int i = 0; i < 16; i += 2)
    stsm4(ot + (i >> 3) * 2048 + (lane & 15) * 128 + (((i + (lane >> 4)) ^ lane) & 7) * 16, pack_bf(oc[4 * i], oc[4 * i + 1]),
          pack_bf(oc[4 * i + 2], oc[4 * i + 3]), pack_bf(oc[4 * i + 4], oc[4 * i + 5]), pack_bf(oc[4 * i + 6], oc[4 * i + 7]));
  asm volatile("fence.proxy.async.shared::cta;" ::: "memory");
  __syncwarp();
  e_store3d(&mout, ot, (rt * 4 + (hp >> 2)) * 64 + w * 16, (hp & 3) * 2);
  TS(wg * 16 + 11);
  GT(61 + wg);
  if (w == 0) TSDUMP(0);
  if (w == 1) TSDUMP(48);
}

typedef CUresult (*EncodeFn)(CUtensorMap*, CUtensorMapDataType, cuuint32_t, void*, const cuuint64_t*, const cuuint64_t*,
                             const cuuint32_t*, const cuuint32_t*, CUtensorMapInterleave, CUtensorMapSwizzle,
                             CUtensorMapL2promotion, CUtensorMapFloatOOBfill);

}

extern "C" void kernel_launch(void* const* d_in, const int* in_sizes, int n_in, void* d_out, int out_size) {
  (void)in_sizes; (void)n_in; (void)out_size;
  void* fn = nullptr;
  cudaDriverEntryPointQueryResult qr;
  cudaGetDriverEntryPoint("cuTensorMapEncodeTiled", &fn, cudaEnableDefault, &qr);
  EncodeFn enc = (EncodeFn)fn;
  CUtensorMap mx, mw, mo, mu, mout, mw4;
  const cuuint32_t es[5] = {1, 1, 1, 1, 1};
  {
    cuuint64_t dims[2] = {512, 2048}, st[1] = {1024};
    cuuint32_t box[2] = {64, 128};
    enc(&mx, CU_TENSOR_MAP_DATA_TYPE_BFLOAT16, 2, d_in[0], dims, st, box, es, CU_TENSOR_MAP_INTERLEAVE_NONE,
        CU_TENSOR_MAP_SWIZZLE_128B, CU_TENSOR_MAP_L2_PROMOTION_L2_128B, CU_TENSOR_MAP_FLOAT_OOB_FILL_NONE);
  }
  {
    cuuint64_t dims[3] = {512, 512, 3}, st[2] = {3072, 1024};
    cuuint32_t box[3] = {32, 64, 3};
    enc(&mw, CU_TENSOR_MAP_DATA_TYPE_BFLOAT16, 3, d_in[1], dims, st, box, es, CU_TENSOR_MAP_INTERLEAVE_NONE,
        CU_TENSOR_MAP_SWIZZLE_64B, CU_TENSOR_MAP_L2_PROMOTION_L2_128B, CU_TENSOR_MAP_FLOAT_OOB_FILL_NONE);
  }
  {
    cuuint64_t dims[3] = {64, 512, 8}, st[2] = {1024, 128};
    cuuint32_t box[3] = {64, 64, 2};
    enc(&mo, CU_TENSOR_MAP_DATA_TYPE_BFLOAT16, 3, d_in[3], dims, st, box, es, CU_TENSOR_MAP_INTERLEAVE_NONE,
        CU_TENSOR_MAP_SWIZZLE_128B, CU_TENSOR_MAP_L2_PROMOTION_L2_128B, CU_TENSOR_MAP_FLOAT_OOB_FILL_NONE);
  }
  {
    cuuint64_t dims[5] = {512, 2, 4, 4, 64}, st[4] = {1024, 8192, 2048, 32768};
    cuuint32_t box[5] = {64, 2, 4, 4, 4};
    enc(&mu, CU_TENSOR_MAP_DATA_TYPE_BFLOAT16, 5, d_in[4], dims, st, box, es, CU_TENSOR_MAP_INTERLEAVE_NONE,
        CU_TENSOR_MAP_SWIZZLE_128B, CU_TENSOR_MAP_L2_PROMOTION_L2_128B, CU_TENSOR_MAP_FLOAT_OOB_FILL_NONE);
  }
  {
    cuuint64_t dims[3] = {64, 2048, 16}, st[2] = {2048, 128};
    cuuint32_t box[3] = {64, 16, 2};
    enc(&mout, CU_TENSOR_MAP_DATA_TYPE_BFLOAT16, 3, d_out, dims, st, box, es, CU_TENSOR_MAP_INTERLEAVE_NONE,
        CU_TENSOR_MAP_SWIZZLE_128B, CU_TENSOR_MAP_L2_PROMOTION_NONE, CU_TENSOR_MAP_FLOAT_OOB_FILL_NONE);
  }
  {
    cuuint64_t dims[4] = {512, 64, 3, 8}, st[3] = {3072, 1024, 64 * 3072};
    cuuint32_t box[4] = {32, 64, 3, 4};
    enc(&mw4, CU_TENSOR_MAP_DATA_TYPE_BFLOAT16, 4, d_in[1], dims, st, box, es, CU_TENSOR_MAP_INTERLEAVE_NONE,
        CU_TENSOR_MAP_SWIZZLE_64B, CU_TENSOR_MAP_L2_PROMOTION_L2_128B, CU_TENSOR_MAP_FLOAT_OOB_FILL_NONE);
  }
  Params P;
  P.x = (const __nv_bfloat16*)d_in[0];
  P.wphi = (const __nv_bfloat16*)d_in[2];
  P.wo = (const __nv_bfloat16*)d_in[3];
  P.logA = (const __nv_bfloat16*)d_in[5];
  P.Aim = (const __nv_bfloat16*)d_in[6];
  P.Cre = (const __nv_bfloat16*)d_in[7];
  P.Cim = (const __nv_bfloat16*)d_in[8];
  P.logdt = (const __nv_bfloat16*)d_in[9];
  P.Dskip = (const __nv_bfloat16*)d_in[10];
  P.out = (__nv_bfloat16*)d_out;
  cudaGetSymbolAddress((void**)&P.xs, g_x);
  P.ts = nullptr;
  cudaFuncSetAttribute(fused_kernel, cudaFuncAttributeMaxDynamicSharedMemorySize, SMEM_BYTES);
  fused_kernel<<<NCTA, NTHREADS, SMEM_BYTES>>>(P, mx, mw, mo, mu, mout, mw4);
}
```

```cpp
#include <cuda_runtime.h>
#include <cuda_bf16.h>
#include <cuda_fp16.h>
#include <cuda.h>
#include <stdint.h>

#define DBG_TS 0

namespace {

constexpr int NTHREADS = 512;
constexpr int NCTA = 128;
constexpr int OFF_W = 0;
constexpr int OFF_X = 98304;
constexpr int OFF_U = OFF_X + 65536;
constexpr int U_CH = 4416, U_ODD = 2240, U_PAD = 128;
constexpr int OFF_STG0 = OFF_U + 18432;
constexpr int SLAB = 3328;
constexpr int OFF_T = OFF_STG0 + 8 * SLAB;
constexpr int T_CH = 5216;
constexpr int T_D = 0;
constexpr int T_5 = 2144;
constexpr int T_3 = T_5 + 384;
constexpr int T_7 = T_5 + 1024;
constexpr int T_9 = T_7 + 320;
constexpr int T_KC = T_9 + 320;
constexpr int T_ST = T_5 - 1024;
constexpr int OFF_PHI = OFF_T + 4 * T_CH;
constexpr int OFF_EYE = OFF_PHI + 1024, OFF_ONE = OFF_EYE + 512;
constexpr int OFF_BAR = OFF_ONE + 256;
constexpr int SMEM_BYTES = OFF_BAR + 512 + 256 * DBG_TS;
constexpr uint32_t SB = 1024;
static_assert(T_KC + 2 * 656 <= T_CH, "table size");
static_assert(SMEM_BYTES <= 232448, "smem");
constexpr int MB_URAW = 0, MB_FULL = 1  , MB_WO = 17, MB_UFULL = 18, MB_OA = 19, MB_OB = 20, MB_OC = 21,
              MB_EMPTY = 22  , MB_AUX = 38;
__host__ __device__ constexpr uint32_t BAR(int i) { return SB + OFF_BAR + 8 * i; }
constexpr int NB_WG0 = 1, NB_ODONE = 2, NB_ST0 = 3  , NB_KV = 5, NB_YZ = 6, NB_INIT = 7, NB_PREP = 8, NB_PROD = 9, NB_KREAD = 10, NB_BDONE = 11, NB_ZERO = 12;
#define U_AT 2
#define ZERO_STEP 15
constexpr int SPIN_MAX = 1 << 16;

constexpr int X_CNT = 0;
constexpr int X_PART = 128;
constexpr int X_O = X_PART + 16 * 8 * 144;
constexpr int X_Y = X_O + 32 * 32 * 128;
constexpr int X_UT = X_Y + 512 * 8 * 32;
constexpr int X_SIZE = X_UT + 512 * (U_CH / 16);
__device__ __align__(128) uint4 g_x[X_SIZE];
extern __shared__ uint8_t smem_raw[];
#define TS(i) do {} while (0)
#define TS1(i) do {} while (0)
#define GT(i) do {} while (0)
#define TSDUMP(base) do {} while (0)

__device__ __forceinline__ uint32_t smem_u32(const void* p) { return (uint32_t)__cvta_generic_to_shared(p); }
__device__ __forceinline__ void mbar_arrive(uint32_t b) {
  asm volatile("mbarrier.arrive.shared::cta.b64 _, [%0];" ::"r"(b) : "memory");
}
__device__ __forceinline__ void mbar_wait(uint32_t b) {
  uint32_t done = 0;
#pragma unroll 1
  for (int i = 0; i < SPIN_MAX && !done; i++) {
    asm volatile("{\n.reg .pred p;\nmbarrier.try_wait.parity.shared::cta.b64 p, [%1], 0, 4000;\nselp.u32 %0, 1, 0, p;\n}\n"
                 : "=r"(done) : "r"(b) : "memory");
  }
}
__device__ __forceinline__ void mbar_spin(uint32_t b) {
  uint32_t done = 0;
#pragma unroll 1
  for (int i = 0; i < (SPIN_MAX << 4) && !done; i++) {
    asm volatile("{\n.reg .pred p;\nmbarrier.try_wait.parity.shared::cta.b64 p, [%1], 0;\nselp.u32 %0, 1, 0, p;\n}\n"
                 : "=r"(done) : "r"(b) : "memory");
  }
}
__device__ __forceinline__ void mbar_init(uint32_t b, int n) {
  asm volatile("mbarrier.init.shared::cta.b64 [%0], %1;" ::"r"(b), "r"(n) : "memory");
}
__device__ __forceinline__ void mbar_expect(uint32_t b, int bytes) {
  asm volatile("mbarrier.arrive.expect_tx.shared::cta.b64 _, [%0], %1;" ::"r"(b), "r"(bytes) : "memory");
}
__device__ __forceinline__ void nb_sync(int id, int n) { asm volatile("bar.sync %0, %1;" ::"r"(id), "r"(n) : "memory"); }
__device__ __forceinline__ void nb_arrive(int id, int n) { asm volatile("bar.arrive %0, %1;" ::"r"(id), "r"(n) : "memory"); }
#define ELECT "{\n.reg .pred p;\nelect.sync _|p, 0xffffffff;\n@p "
__device__ __forceinline__ void e_expect(uint32_t b, int bytes) {
  asm volatile(ELECT "mbarrier.arrive.expect_tx.shared::cta.b64 _, [%0], %1;\n}\n" ::"r"(b), "r"(bytes) : "memory");
}
__device__ __forceinline__ void e_tma2d(uint32_t dst, const CUtensorMap* m, uint32_t bar, int c0, int c1) {
  asm volatile(ELECT "cp.async.bulk.tensor.2d.shared::cluster.global.mbarrier::complete_tx::bytes [%0], [%1, {%3,%4}], [%2];\n}\n"
               ::"r"(dst), "l"(m), "r"(bar), "r"(c0), "r"(c1) : "memory");
}
__device__ __forceinline__ void e_tma3d(uint32_t dst, const CUtensorMap* m, uint32_t bar, int c0, int c1, int c2) {
  asm volatile(ELECT "cp.async.bulk.tensor.3d.shared::cluster.global.mbarrier::complete_tx::bytes [%0], [%1, {%3,%4,%5}], [%2];\n}\n"
               ::"r"(dst), "l"(m), "r"(bar), "r"(c0), "r"(c1), "r"(c2) : "memory");
}
__device__ __forceinline__ void e_tma4d(uint32_t dst, const CUtensorMap* m, uint32_t bar, int c0, int c3) {
  asm volatile(ELECT "cp.async.bulk.tensor.4d.shared::cluster.global.mbarrier::complete_tx::bytes [%0], [%1, {%3,%5,%5,%4}], [%2];\n}\n"
               ::"r"(dst), "l"(m), "r"(bar), "r"(c0), "r"(c3), "r"(0) : "memory");
}
__device__ __forceinline__ void e_tma5d(uint32_t dst, const CUtensorMap* m, uint32_t bar, int c0, int c4) {
  asm volatile(ELECT "cp.async.bulk.tensor.5d.shared::cluster.global.mbarrier::complete_tx::bytes [%0], [%1, {%3,%5,%5,%5,%4}], [%2];\n}\n"
               ::"r"(dst), "l"(m), "r"(bar), "r"(c0), "r"(c4), "r"(0) : "memory");
}
__device__ __forceinline__ void e_bulk(uint32_t dst, const void* src, int bytes, uint32_t bar) {
  asm volatile(ELECT "cp.async.bulk.shared::cluster.global.mbarrier::complete_tx::bytes [%0], [%1], %2, [%3];\n}\n"
               ::"r"(dst), "l"(src), "r"(bytes), "r"(bar) : "memory");
}
__device__ __forceinline__ void e_prefetch(const void* p, int bytes) {
  asm volatile(ELECT "cp.async.bulk.prefetch.L2.global [%0], %1;\n}\n" ::"l"(p), "r"(bytes) : "memory");
}
__device__ __forceinline__ void e_store3d(const CUtensorMap* m, uint32_t src, int c1, int c2) {
  asm volatile(ELECT "cp.async.bulk.tensor.3d.global.shared::cta.bulk_group [%0, {%4,%2,%3}], [%1];\n"
               "@p cp.async.bulk.commit_group;\n@p cp.async.bulk.wait_group.read 0;\n}\n"
               ::"l"(m), "r"(src), "r"(c1), "r"(c2), "r"(0) : "memory");
}
__host__ __device__ constexpr uint64_t mkdesc(uint32_t addr, uint32_t lbo, uint32_t sbo, int swz) {
  return (uint64_t)((addr & 0x3FFFF) >> 4) | ((uint64_t)(lbo >> 4) << 16) | ((uint64_t)(sbo >> 4) << 32) |
         ((uint64_t)swz << 62);
}
#define WG_FENCE() asm volatile("wgmma.fence.sync.aligned;" ::: "memory")
#define WG_COMMIT() asm volatile("wgmma.commit_group.sync.aligned;" ::: "memory")
#define WG_WAIT(n) asm volatile("wgmma.wait_group.sync.aligned " #n ";" ::: "memory")

__device__ __forceinline__ void mma(float& d0, float& d1, float& d2, float& d3, uint32_t a0, uint32_t a1, uint32_t a2,
                                    uint32_t a3, uint32_t b0, uint32_t b1) {
  asm volatile("mma.sync.aligned.m16n8k16.row.col.f32.bf16.bf16.f32 {%0,%1,%2,%3},{%4,%5,%6,%7},{%8,%9},{%0,%1,%2,%3};"
               : "+f"(d0), "+f"(d1), "+f"(d2), "+f"(d3)
               : "r"(a0), "r"(a1), "r"(a2), "r"(a3), "r"(b0), "r"(b1));
}
__device__ __forceinline__ void mmac(float (&d)[4], uint32_t a0, uint32_t a1, uint32_t a2, uint32_t a3, uint32_t b0,
                                     uint32_t b1, const float (&c)[4]) {
  asm volatile("mma.sync.aligned.m16n8k16.row.col.f32.bf16.bf16.f32 {%0,%1,%2,%3},{%4,%5,%6,%7},{%8,%9},{%10,%11,%12,%13};"
               : "=f"(d[0]), "=f"(d[1]), "=f"(d[2]), "=f"(d[3])
               : "r"(a0), "r"(a1), "r"(a2), "r"(a3), "r"(b0), "r"(b1), "f"(c[0]), "f"(c[1]), "f"(c[2]), "f"(c[3]));
}
__device__ __forceinline__ void mma_p(int p, float (&d)[4], uint32_t a0, uint32_t a1, uint32_t a2, uint32_t a3, uint32_t b0, uint32_t b1) {
  asm volatile("{\n.reg .pred q;\nsetp.ne.b32 q, %10, 0;\n"
               "@q mma.sync.aligned.m16n8k16.row.col.f32.bf16.bf16.f32 {%0,%1,%2,%3},{%4,%5,%6,%7},{%8,%9},{%0,%1,%2,%3};\n}\n"
               : "+f"(d[0]), "+f"(d[1]), "+f"(d[2]), "+f"(d[3])
               : "r"(a0), "r"(a1), "r"(a2), "r"(a3), "r"(b0), "r"(b1), "r"(p));
}
__device__ __forceinline__ void mmac_p(int p, float (&d)[4], uint32_t a0, uint32_t a1, uint32_t a2, uint32_t a3, uint32_t b0,
                                       uint32_t b1, const float (&c)[4]) {
  asm volatile("{\n.reg .pred q;\nsetp.ne.b32 q, %14, 0;\n"
               "@q mma.sync.aligned.m16n8k16.row.col.f32.bf16.bf16.f32 {%0,%1,%2,%3},{%4,%5,%6,%7},{%8,%9},{%10,%11,%12,%13};\n}\n"
               : "+f"(d[0]), "+f"(d[1]), "+f"(d[2]), "+f"(d[3])
               : "r"(a0), "r"(a1), "r"(a2), "r"(a3), "r"(b0), "r"(b1), "f"(c[0]), "f"(c[1]), "f"(c[2]), "f"(c[3]), "r"(p));
}
__device__ __forceinline__ void mma_h(float (&d)[4], const uint32_t (&a)[4], uint32_t b0, uint32_t b1) {
  asm volatile("mma.sync.aligned.m16n8k16.row.col.f32.f16.f16.f32 {%0,%1,%2,%3},{%4,%5,%6,%7},{%8,%9},{%0,%1,%2,%3};"
               : "+f"(d[0]), "+f"(d[1]), "+f"(d[2]), "+f"(d[3]) : "r"(a[0]), "r"(a[1]), "r"(a[2]), "r"(a[3]), "r"(b0), "r"(b1));
}
__device__ __forceinline__ void mma0(float& d0, float& d1, float& d2, float& d3, uint32_t a0, uint32_t a1, uint32_t a2,
                                     uint32_t a3, uint32_t b0, uint32_t b1) {
  asm volatile("mma.sync.aligned.m16n8k16.row.col.f32.bf16.bf16.f32 {%0,%1,%2,%3},{%4,%5,%6,%7},{%8,%9},{%10,%10,%10,%10};"
               : "=f"(d0), "=f"(d1), "=f"(d2), "=f"(d3)
               : "r"(a0), "r"(a1), "r"(a2), "r"(a3), "r"(b0), "r"(b1), "f"(0.f));
}
__device__ __forceinline__ uint32_t pack_bf(float lo, float hi) {
  uint32_t r;
  asm("cvt.rn.bf16x2.f32 %0, %1, %2;" : "=r"(r) : "f"(hi), "f"(lo));
  return r;
}
__device__ __forceinline__ float bf_lo(uint32_t w) { return __uint_as_float(w << 16); }
__device__ __forceinline__ float bf_hi(uint32_t w) { return __uint_as_float(w & 0xffff0000u); }
__device__ __forceinline__ float bf_round(float x) { return __bfloat162float(__float2bfloat16_rn(x)); }
__device__ __forceinline__ uint32_t bmax2(uint32_t a, uint32_t b) {
  uint32_t r; asm("max.bf16x2 %0, %1, %2;" : "=r"(r) : "r"(a), "r"(b)); return r;
}
__device__ __forceinline__ uint32_t bmin2(uint32_t a, uint32_t b) {
  uint32_t r; asm("min.bf16x2 %0, %1, %2;" : "=r"(r) : "r"(a), "r"(b)); return r;
}
__device__ __forceinline__ float ex2(float x) { float r; asm("ex2.approx.ftz.f32 %0, %1;" : "=f"(r) : "f"(x)); return r; }
__device__ __forceinline__ float rcp(float x) { float r; asm("rcp.approx.ftz.f32 %0, %1;" : "=f"(r) : "f"(x)); return r; }
__device__ __forceinline__ void ldsm4(uint32_t (&r)[4], uint32_t a) {
  asm volatile("ldmatrix.sync.aligned.m8n8.x4.shared.b16 {%0,%1,%2,%3}, [%4];"
               : "=r"(r[0]), "=r"(r[1]), "=r"(r[2]), "=r"(r[3]) : "r"(a) : "memory");
}
__device__ __forceinline__ void ldsm4t(uint32_t (&r)[4], uint32_t a) {
  asm volatile("ldmatrix.sync.aligned.m8n8.x4.trans.shared.b16 {%0,%1,%2,%3}, [%4];"
               : "=r"(r[0]), "=r"(r[1]), "=r"(r[2]), "=r"(r[3]) : "r"(a) : "memory");
}
__device__ __forceinline__ void stsm4(uint32_t a, uint32_t r0, uint32_t r1, uint32_t r2, uint32_t r3) {
  asm volatile("stmatrix.sync.aligned.m8n8.x4.shared.b16 [%0], {%1,%2,%3,%4};"
               ::"r"(a), "r"(r0), "r"(r1), "r"(r2), "r"(r3) : "memory");
}
__device__ __forceinline__ uint32_t lds32(uint32_t a) {
  uint32_t r; asm volatile("ld.shared.u32 %0, [%1];" : "=r"(r) : "r"(a) : "memory"); return r;
}
__device__ __forceinline__ uint32_t lds16(uint32_t a) {
  uint32_t r; asm volatile("{\n.reg .u16 h;\nld.shared.u16 h, [%1];\ncvt.u32.u16 %0, h;\n}\n" : "=r"(r) : "r"(a) : "memory"); return r;
}
__device__ __forceinline__ uint2 lds64(uint32_t a) {
  uint2 r; asm volatile("ld.shared.v2.u32 {%0,%1}, [%2];" : "=r"(r.x), "=r"(r.y) : "r"(a) : "memory"); return r;
}
__device__ __forceinline__ uint4 lds128(uint32_t a) {
  uint4 r;
  asm volatile("ld.shared.v4.u32 {%0,%1,%2,%3}, [%4];" : "=r"(r.x), "=r"(r.y), "=r"(r.z), "=r"(r.w) : "r"(a) : "memory");
  return r;
}
__device__ __forceinline__ void sts32(uint32_t a, uint32_t v) { asm volatile("st.shared.u32 [%0], %1;" ::"r"(a), "r"(v) : "memory"); }
__device__ __forceinline__ void sts16(uint32_t a, uint32_t v) {
  asm volatile("{\n.reg .u16 h;\ncvt.u16.u32 h, %1;\nst.shared.u16 [%0], h;\n}\n" ::"r"(a), "r"(v) : "memory");
}
__device__ __forceinline__ void sts64(uint32_t a, uint32_t x, uint32_t y) {
  asm volatile("st.shared.v2.u32 [%0], {%1,%2};" ::"r"(a), "r"(x), "r"(y) : "memory");
}
__device__ __forceinline__ void sts128(uint32_t a, uint32_t x, uint32_t y, uint32_t z, uint32_t w) {
  asm volatile("st.shared.v4.u32 [%0], {%1,%2,%3,%4};" ::"r"(a), "r"(x), "r"(y), "r"(z), "r"(w) : "memory");
}
__device__ __forceinline__ uint4 ld_x(const uint4* p) {
  uint4 r;
  asm volatile("{\n.reg .b128 t;\nld.relaxed.gpu.global.b128 t, [%4];\nmov.b128 {%0,%1,%2,%3}, t;\n}\n"
               : "=r"(r.x), "=r"(r.y), "=r"(r.z), "=r"(r.w) : "l"(p) : "memory");
  return r;
}
__device__ __forceinline__ uint32_t ld_x32(const uint32_t* p) {
  uint32_t r; asm volatile("ld.relaxed.gpu.global.u32 %0, [%1];" : "=r"(r) : "l"(p) : "memory"); return r;
}
__device__ __forceinline__ void st_x(uint4* p, uint32_t x, uint32_t y, uint32_t z, uint32_t w) {
  asm volatile("{\n.reg .b128 t;\nmov.b128 t, {%1,%2,%3,%4};\nst.relaxed.gpu.global.b128 [%0], t;\n}\n"
               ::"l"(p), "r"(x), "r"(y), "r"(z), "r"(w) : "memory");
}
__device__ __forceinline__ void st_x_p(int p, uint4* a, uint32_t x, uint32_t y, uint32_t z, uint32_t w) {
  asm volatile("{\n.reg .b128 t;\n.reg .pred q;\nsetp.ne.b32 q, %5, 0;\nmov.b128 t, {%1,%2,%3,%4};\n@q st.relaxed.gpu.global.b128 [%0], t;\n}\n"
               ::"l"(a), "r"(x), "r"(y), "r"(z), "r"(w), "r"(p) : "memory");
}
__device__ __forceinline__ void sts64_p(int p, uint32_t a, uint32_t x, uint32_t y) {
  asm volatile("{\n.reg .pred q;\nsetp.ne.b32 q, %3, 0;\n@q st.shared.v2.u32 [%0], {%1,%2};\n}\n" ::"r"(a), "r"(x), "r"(y), "r"(p) : "memory");
}
__device__ __forceinline__ void st_x32(uint32_t* p, uint32_t x) {
  asm volatile("st.relaxed.gpu.global.u32 [%0], %1;" ::"l"(p), "r"(x) : "memory");
}
__device__ __forceinline__ uint32_t nz(uint32_t w) { return max(w, 1u); }
__device__ __forceinline__ uint32_t fu(float x) { return __float_as_uint(x); }
__device__ __forceinline__ float uf(uint32_t x) { return __uint_as_float(x); }

__device__ __forceinline__ void wgmma_ss_n96(float (&d)[48], uint64_t da, uint64_t db, int sc) {
  asm volatile("{\n.reg .pred p;\nsetp.ne.b32 p, %50, 0;\n"
      "wgmma.mma_async.sync.aligned.m64n96k16.f32.bf16.bf16 "
      "{%0,%1,%2,%3,%4,%5,%6,%7,%8,%9,%10,%11,%12,%13,%14,%15,%16,%17,%18,%19,%20,%21,%22,%23,%24,%25,%26,%27,%28,%29,%30,%31,%32,%33,%34,%35,%36,%37,%38,%39,%40,%41,%42,%43,%44,%45,%46,%47}, "
      "%48, %49, p, 1, 1, 0, 1;\n}\n"
      : "+f"(d[0]), "+f"(d[1]), "+f"(d[2]), "+f"(d[3]), "+f"(d[4]), "+f"(d[5]), "+f"(d[6]), "+f"(d[7]),
        "+f"(d[8]), "+f"(d[9]), "+f"(d[10]), "+f"(d[11]), "+f"(d[12]), "+f"(d[13]), "+f"(d[14]), "+f"(d[15]),
        "+f"(d[16]), "+f"(d[17]), "+f"(d[18]), "+f"(d[19]), "+f"(d[20]), "+f"(d[21]), "+f"(d[22]), "+f"(d[23]),
        "+f"(d[24]), "+f"(d[25]), "+f"(d[26]), "+f"(d[27]), "+f"(d[28]), "+f"(d[29]), "+f"(d[30]), "+f"(d[31]),
        "+f"(d[32]), "+f"(d[33]), "+f"(d[34]), "+f"(d[35]), "+f"(d[36]), "+f"(d[37]), "+f"(d[38]), "+f"(d[39]),
        "+f"(d[40]), "+f"(d[41]), "+f"(d[42]), "+f"(d[43]), "+f"(d[44]), "+f"(d[45]), "+f"(d[46]), "+f"(d[47])
      : "l"(da), "l"(db), "r"(sc));
}

__device__ __forceinline__ void wgmma_ss_n128(float (&d)[64], uint64_t da, uint64_t db, int sc) {
  asm volatile("{\n.reg .pred p;\nsetp.ne.b32 p, %66, 0;\n"
      "wgmma.mma_async.sync.aligned.m64n128k16.f32.bf16.bf16 "
      "{%0,%1,%2,%3,%4,%5,%6,%7,%8,%9,%10,%11,%12,%13,%14,%15,%16,%17,%18,%19,%20,%21,%22,%23,%24,%25,%26,%27,%28,%29,%30,%31,%32,%33,%34,%35,%36,%37,%38,%39,%40,%41,%42,%43,%44,%45,%46,%47,%48,%49,%50,%51,%52,%53,%54,%55,%56,%57,%58,%59,%60,%61,%62,%63}, "
      "%64, %65, p, 1, 1, 0, 1;\n}\n"
      : "+f"(d[0]), "+f"(d[1]), "+f"(d[2]), "+f"(d[3]), "+f"(d[4]), "+f"(d[5]), "+f"(d[6]), "+f"(d[7]),
        "+f"(d[8]), "+f"(d[9]), "+f"(d[10]), "+f"(d[11]), "+f"(d[12]), "+f"(d[13]), "+f"(d[14]), "+f"(d[15]),
        "+f"(d[16]), "+f"(d[17]), "+f"(d[18]), "+f"(d[19]), "+f"(d[20]), "+f"(d[21]), "+f"(d[22]), "+f"(d[23]),
        "+f"(d[24]), "+f"(d[25]), "+f"(d[26]), "+f"(d[27]), "+f"(d[28]), "+f"(d[29]), "+f"(d[30]), "+f"(d[31]),
        "+f"(d[32]), "+f"(d[33]), "+f"(d[34]), "+f"(d[35]), "+f"(d[36]), "+f"(d[37]), "+f"(d[38]), "+f"(d[39]),
        "+f"(d[40]), "+f"(d[41]), "+f"(d[42]), "+f"(d[43]), "+f"(d[44]), "+f"(d[45]), "+f"(d[46]), "+f"(d[47]),
        "+f"(d[48]), "+f"(d[49]), "+f"(d[50]), "+f"(d[51]), "+f"(d[52]), "+f"(d[53]), "+f"(d[54]), "+f"(d[55]),
        "+f"(d[56]), "+f"(d[57]), "+f"(d[58]), "+f"(d[59]), "+f"(d[60]), "+f"(d[61]), "+f"(d[62]), "+f"(d[63])
      : "l"(da), "l"(db), "r"(sc));
}

__device__ __forceinline__ void wgmma_ss_n40(float (&d)[20], uint64_t da, uint64_t db, int sc) {
  asm volatile("{\n.reg .pred p;\nsetp.ne.b32 p, %22, 0;\n"
      "wgmma.mma_async.sync.aligned.m64n40k16.f32.bf16.bf16 "
      "{%0,%1,%2,%3,%4,%5,%6,%7,%8,%9,%10,%11,%12,%13,%14,%15,%16,%17,%18,%19}, "
      "%20, %21, p, 1, 1, 1, 1;\n}\n"
      : "+f"(d[0]), "+f"(d[1]), "+f"(d[2]), "+f"(d[3]), "+f"(d[4]), "+f"(d[5]), "+f"(d[6]), "+f"(d[7]),
        "+f"(d[8]), "+f"(d[9]), "+f"(d[10]), "+f"(d[11]), "+f"(d[12]), "+f"(d[13]), "+f"(d[14]), "+f"(d[15]),
        "+f"(d[16]), "+f"(d[17]), "+f"(d[18]), "+f"(d[19])
      : "l"(da), "l"(db), "r"(sc));
}

__device__ __forceinline__ void wgmma_rs_n8(float (&d)[4], const uint4& a, uint64_t db, int sc) {
  asm volatile("{\n.reg .pred p;\nsetp.ne.b32 p, %9, 0;\n"
      "wgmma.mma_async.sync.aligned.m64n8k16.f32.bf16.bf16 "
      "{%0,%1,%2,%3}, "
      "{%4,%5,%6,%7}, %8, p, 1, 1, 1;\n}\n"
      : "+f"(d[0]), "+f"(d[1]), "+f"(d[2]), "+f"(d[3])
      : "r"(a.x), "r"(a.y), "r"(a.z), "r"(a.w), "l"(db), "r"(sc));
}

__device__ __forceinline__ void wgmma_rs_n16(float (&d)[8], const uint4& a, uint64_t db, int sc) {
  asm volatile("{\n.reg .pred p;\nsetp.ne.b32 p, %13, 0;\n"
      "wgmma.mma_async.sync.aligned.m64n16k16.f32.bf16.bf16 "
      "{%0,%1,%2,%3,%4,%5,%6,%7}, "
      "{%8,%9,%10,%11}, %12, p, 1, 1, 1;\n}\n"
      : "+f"(d[0]), "+f"(d[1]), "+f"(d[2]), "+f"(d[3]), "+f"(d[4]), "+f"(d[5]), "+f"(d[6]), "+f"(d[7])
      : "r"(a.x), "r"(a.y), "r"(a.z), "r"(a.w), "l"(db), "r"(sc));
}

__device__ __forceinline__ void wgmma_rs_n24(float (&d)[12], const uint4& a, uint64_t db, int sc) {
  asm volatile("{\n.reg .pred p;\nsetp.ne.b32 p, %17, 0;\n"
      "wgmma.mma_async.sync.aligned.m64n24k16.f32.bf16.bf16 "
      "{%0,%1,%2,%3,%4,%5,%6,%7,%8,%9,%10,%11}, "
      "{%12,%13,%14,%15}, %16, p, 1, 1, 1;\n}\n"
      : "+f"(d[0]), "+f"(d[1]), "+f"(d[2]), "+f"(d[3]), "+f"(d[4]), "+f"(d[5]), "+f"(d[6]), "+f"(d[7]),
        "+f"(d[8]), "+f"(d[9]), "+f"(d[10]), "+f"(d[11])
      : "r"(a.x), "r"(a.y), "r"(a.z), "r"(a.w), "l"(db), "r"(sc));
}

struct Params {
  const __nv_bfloat16 *logA, *Aim, *Cre, *Cim, *logdt, *Dskip, *x, *wphi, *wo;
  __nv_bfloat16* out;
  uint4* xs;
  long long* ts;
};

__device__ __forceinline__ uint4 tr_row(const uint4 (&v)[8], int i) {
  uint32_t o[4];
#pragma unroll
  for (int m = 0; m < 4; m++) {
    const uint4 &ra = v[2 * m], &rb = v[2 * m + 1];
    const int k = i >> 1;
    const uint32_t xa = k == 0 ? ra.x : k == 1 ? ra.y : k == 2 ? ra.z : ra.w;
    const uint32_t xb = k == 0 ? rb.x : k == 1 ? rb.y : k == 2 ? rb.z : rb.w;
    o[m] = __byte_perm(xa, xb, (i & 1) ? 0x7632 : 0x5410);
  }
  return make_uint4(o[0], o[1], o[2], o[3]);
}

struct cpx { float r, i; };
__device__ __forceinline__ cpx csq(cpx a) { return {a.r * a.r - a.i * a.i, 2.f * (a.r * a.i)}; }
__device__ __forceinline__ cpx polar(float e, float t) {
  const float m = ex2(e);
  return {m * __cosf(t), m * __sinf(t)};
}

struct KgenRaw { unsigned short la, ai, cr, ci, ldt; };
__device__ __forceinline__ KgenRaw kgen_load(const Params& P, int d, int unit, int lane) {
  const int o = d * 128 + unit * 32 + lane;
  return {__ldg((const unsigned short*)P.logA + o), __ldg((const unsigned short*)P.Aim + o), __ldg((const unsigned short*)P.Cre + o),
          __ldg((const unsigned short*)P.Cim + o), __ldg((const unsigned short*)P.logdt + d)};
}
struct hmul { __half2 a, b; };
__device__ __forceinline__ hmul mk_mul(cpx w) {
  uint32_t b;
  asm("{\n.reg .f32 n;\nneg.ftz.f32 n, %1;\ncvt.rn.f16x2.f32 %0, %2, n;\n}\n" : "=r"(b) : "f"(w.i), "f"(w.r));
  return {__floats2half2_rn(w.r, w.i), *(const __half2*)&b};
}
__device__ __forceinline__ __half2 hcm(__half2 z, const hmul& w) { return __hfma2(__high2half2(z), w.b, __hmul2(__low2half2(z), w.a)); }
__device__ __forceinline__ uint32_t hu(__half2 v) { return *(const uint32_t*)&v; }

struct KgenAddr { uint32_t sa, sb, lb, lc, la; };
__device__ __forceinline__ KgenAddr kgen_addr(int lane, uint32_t buf) {
  KgenAddr a;
  a.sa = buf + (lane & 7) * 128 + ((((lane >> 3) ^ lane) & 7) << 4);
  a.lb = buf + (lane >> 3) * 128 + (((lane ^ (lane >> 3)) & 7) << 4);
  a.la = buf + ((lane >> 3) & 1) * 1024 + (lane >> 4) * 128 + (((lane ^ (lane >> 4)) & 7) << 4);
  a.sb = a.sa ^ 64; a.lc = a.lb ^ 64;
  asm volatile("" : "+r"(a.sa), "+r"(a.sb), "+r"(a.lb), "+r"(a.lc), "+r"(a.la));
  return a;
}
__device__ __forceinline__ void kgen_unit(const KgenRaw& r, const KgenAddr& ad, uint32_t zero, float (&k)[5][4], float& k2048, float& sc) {
  const float dt = bf_round(expf(bf_lo(r.ldt)));
  const float a2 = bf_round(ex2(bf_lo(r.la) * 1.4426950408889634f)) * (dt * -1.4426950408889634f);
  const float f = bf_lo(r.ai) * dt;
  const float r128 = f * 20.371832715762604f;
  const uint32_t ex = min(max(__reduce_max_sync(0xffffffffu, max(r.cr & 0x7fffu, r.ci & 0x7fffu)) >> 7, 1u), 253u);
  const float cs = uf((254u - ex) << 23);
  sc = 2.f * dt * uf(ex << 23);
  const cpx C = {bf_lo(r.cr) * cs, -bf_lo(r.ci) * cs};
  auto put = [&](const __half2 (&v)[8], uint32_t off) {
    stsm4(ad.sa + off, hu(v[0]), hu(v[1]), hu(v[2]), hu(v[3]));
    stsm4(ad.sb + off, hu(v[4]), hu(v[5]), hu(v[6]), hu(v[7]));
  };
  uint32_t A[4][4], B[5][2][4];
  auto get = [&](int j, uint32_t off) {
    __syncwarp();
    ldsm4(B[j][0], ad.lb + off);
    ldsm4(B[j][1], ad.lc + 512 + off);
  };
  auto tile = [&](int j) {
    k[j][0] = k[j][1] = k[j][2] = k[j][3] = 0.f;
#pragma unroll
    for (int s = 0; s < 4; s++) mma_h(k[j], A[s], B[j][s >> 1][2 * (s & 1)], B[j][s >> 1][2 * (s & 1) + 1]);
  };
  auto after = [&](cpx v, uint32_t dep) { return cpx{uf(fu(v.r) ^ (dep & zero)), v.i}; };
  const cpx w1 = polar(a2, f), w128 = polar(a2 * 128.f, (r128 - rintf(r128)) * 6.283185307179586f);
  const cpx w2 = csq(w1), w4 = csq(w2);
  __half2 t0[8], t1[8], t2[8], t3[8], t4[8];
  const hmul m2 = mk_mul(w2), m4 = mk_mul(w4), m128 = mk_mul(w128);
  t0[0] = __floats2half2_rn(1.f, 0.f); t0[1] = __floats2half2_rn(w1.r, w1.i); t0[2] = m2.a; t0[4] = m4.a;
  t0[3] = hcm(t0[1], m2); t0[5] = hcm(t0[1], m4); t0[6] = hcm(t0[2], m4); t0[7] = hcm(t0[3], m4);
  put(t0, 0); get(0, 0);
  t1[0] = m128.a;
#pragma unroll
  for (int i = 1; i < 8; i++) t1[i] = hcm(t0[i], m128);
  put(t1, 1024); get(1, 1024);
  {
    cpx w8 = csq(after(w4, B[0][0][0]));
    w8.i = -w8.i;
    const cpx w16 = csq(w8), w32 = csq(w16), w64 = csq(w32);
    const hmul m8 = mk_mul(w8), m16 = mk_mul(w16), m32 = mk_mul(w32), m64 = mk_mul(w64);
    __half2 a[8];
    a[0] = __floats2half2_rn(C.r, C.i); a[1] = hcm(a[0], m8);
    a[2] = hcm(a[0], m16); a[3] = hcm(a[1], m16);
#pragma unroll
    for (int i = 0; i < 4; i++) a[4 + i] = hcm(a[i], m32);
    put(a, 0);
#pragma unroll
    for (int i = 0; i < 8; i++) a[i] = hcm(a[i], m64);
    put(a, 1024);
    __syncwarp();
#pragma unroll
    for (int s = 0; s < 4; s++) ldsm4(A[s], (ad.la ^ (s << 5)) + s * 256);
  }
  const cpx w256 = csq(after(w128, B[1][0][0]));
  const hmul m256 = mk_mul(w256);
  t2[0] = m256.a;
#pragma unroll
  for (int i = 1; i < 8; i++) t2[i] = hcm((i & 1) ? t1[i & 6] : t0[i & 6], m256);
  put(t2, 0); get(2, 0);
  tile(0); tile(1);
  const cpx w512 = csq(after(w256, A[0][0]));
  const hmul m512 = mk_mul(w512);
  t3[0] = m512.a;
#pragma unroll
  for (int i = 1; i < 8; i++) t3[i] = hcm((i & 2) ? t2[i & 5] : ((i & 1) ? t1[i & 4] : t0[i & 4]), m512);
  put(t3, 1024); get(3, 1024);
  tile(2);
  const cpx w1024 = csq(after(w512, B[2][0][0])), we = csq(w1024);
  const hmul m1024 = mk_mul(w1024);
  t4[0] = m1024.a;
#pragma unroll
  for (int i = 1; i < 8; i++) t4[i] = hcm((i & 4) ? t3[i & 3] : ((i & 2) ? t2[i & 1] : t1[0]), m1024);
  put(t4, 0); get(4, 0);
  tile(3); tile(4);
  k2048 = (C.r * we.r + C.i * we.i) * sc;
}

__device__ __forceinline__ void build_tables(uint32_t tb, int lane, float (&k)[5][4], float k2048) {
  const int g = lane >> 2, c = lane & 3;
  const uint32_t kc = tb + T_KC + 16;
  {
    const uint32_t a0 = kc + 16 * g + 4 * c, a2 = kc + 2 * (256 + 4 * g + c);
    const uint32_t a3 = kc + 2 * (384 + 2 * g + 64 * (c & 1) + (c >> 1)), a4 = kc + 2 * (512 + g + 32 * c);
#pragma unroll
    for (int r = 0; r < 2; r++) {
      sts32(a0 + 128 * r, pack_bf(k[0][2 * r], k[0][2 * r + 1]));
      sts32(a0 + 128 * r + 256, pack_bf(k[1][2 * r], k[1][2 * r + 1]));
      const uint32_t w2 = pack_bf(k[2][2 * r], k[2][2 * r + 1]);
      const uint32_t w3 = pack_bf(k[3][2 * r], k[3][2 * r + 1]);
      const uint32_t w4 = pack_bf(k[4][2 * r], k[4][2 * r + 1]);
      sts16(a2 + 64 * r, w2); sts16(a2 + 64 * r + 128, w2 >> 16);
      sts16(a3 + 32 * r, w3); sts16(a3 + 32 * r + 64, w3 >> 16);
      sts16(a4 + 16 * r, w4); sts16(a4 + 16 * r + 32, w4 >> 16);
    }
  }
  if (lane == 0) { sts16(kc + 2 * 640, pack_bf(k2048, 0.f)); sts16(kc - 2, 0); }
  __syncwarp();
  const uint32_t td = tb + T_D + 32;
  {
    const uint4 v = lds128(kc + 16 * lane);
    const uint32_t pv = lds16(kc + 16 * lane - 2);
    sts128(td + 32 * lane, __byte_perm(v.x, pv, 0x5410), __byte_perm(v.x, v.x, 0x1032), __byte_perm(v.y, v.x, 0x7610),
           __byte_perm(v.y, v.y, 0x1032));
    sts128(td + 32 * lane + 16, __byte_perm(v.z, v.y, 0x7610), __byte_perm(v.z, v.z, 0x1032),
           __byte_perm(v.w, v.z, 0x7610), __byte_perm(v.w, v.w, 0x1032));
  }
  {
    const uint2 v = lds64(kc + 512 + 8 * lane);
    const uint32_t k4 = lds16(kc + 512 + 8 * lane + 8);
    const uint32_t pv = lds16(kc + (lane == 0 ? 510 : 512 + 8 * lane));
    const uint32_t k22 = __byte_perm(v.y, v.y, 0x1010);
    sts128(td + 1024 + 32 * lane, __byte_perm(v.x, pv, 0x5410), __byte_perm(v.x, v.x, 0x1010),
           __byte_perm(v.x, v.x, 0x1032), __byte_perm(v.y, v.x, 0x7610));
    sts128(td + 1024 + 32 * lane + 16, k22, k22, __byte_perm(v.y, v.y, 0x1032), __byte_perm(k4, v.y, 0x7610));
  }
  {
    const uint32_t kk = lds16(kc + 2 * 384);
    const uint32_t w = lane < 3 ? (kk | (kk << 16)) : (lane == 3 ? (kk << 16) : 0u);
    if (lane < 24) sts32(td + 4 * (lane < 16 ? 512 + lane : lane - 24), w);
    const uint32_t lo_ = lds16(kc + 2 * 511), le_ = lds16(kc + 2 * 512);
    const uint32_t ja = tb + T_5 + (lane < 16 ? 4 * lane : 256 + 4 * lane);
    sts32(ja, lane == 16 ? (le_ << 16) : 0u);
    sts32(ja + 384, lane == 16 ? (lo_ << 16) : 0u);
    sts32(tb + (lane < 16 ? T_7 : T_9 - 64) + 4 * lane, 0u);
  }
#pragma unroll
  for (int s = 0; s < 2; s++) {
    const uint32_t b = kc + 2 * (s ? 512 : 384) + 8 * lane;
    const uint2 v = lds64(b);
    uint32_t em = lds16(b - 2), e0 = v.x;
    const uint32_t e4 = lds16(b + 8);
    if (lane == 0) { em = 0; e0 = 0; }
    sts64(tb + (s ? T_7 : T_3) + 64 + 8 * lane, __byte_perm(v.x, em, 0x5432), __byte_perm(v.y, v.x, 0x7632));
    sts64(tb + (s ? T_9 : T_5) + 64 + 8 * lane, __byte_perm(v.y, e0, 0x5410), __byte_perm(e4, v.y, 0x5410));
  }
  __syncwarp();
}

__device__ __forceinline__ uint32_t box2w(int lo, int n, int o) {
  return ((unsigned)(o - lo) < (unsigned)n ? 0x3F80u : 0u) | ((unsigned)(o + 1 - lo) < (unsigned)n ? 0x3F800000u : 0u);
}

#define SPLIT() asm volatile("{\n.reg .pred p;\nsetp.ne.u32 p, %0, 0;\n@p exit;\n}\n" ::"r"(blockIdx.y) : "memory")

__device__ __forceinline__ void conv_channel(uint32_t ub, uint32_t tb, int lane, uint4* ydst) {
  const int g = lane >> 2, c = lane & 3, x = g - 2 * c;
  const int mi = lane >> 3;
  const uint32_t qa = ub + U_PAD + 16 * (lane & 7) + ((mi == 0 || mi == 3) ? U_ODD : 0) - (mi == 0 ? 16 : 0);
  const uint32_t hb = ub + U_PAD + (mi & 1) * U_ODD + 16 * ((lane >> 4) + (lane & 7)) - 16;
  const uint32_t kv = lds16(tb + T_KC + 16 + 2 * 512);
  const int oh = c < 2 ? 8 + 2 * c : 2 * c - 8, og = c < 3 ? 2 * c : -10;
  uint32_t bx[4] = {box2w(g - 4, 9, 2 * c), box2w(g - 3, 7, 2 * c), box2w(g - 4, 9, oh), box2w(g - 3, 7, oh)};
  uint32_t by[4] = {box2w(g - 10, 5, 2 * c - 8), box2w(g - 5, 3, 2 * c - 8), box2w(g - 10, 5, og), box2w(g - 5, 3, og)};
  uint32_t lb0 = ((unsigned)(x + 5) < 2u ? kv : 0u) | ((unsigned)(x + 4) < 2u ? kv << 16 : 0u);
  uint32_t lb1 = ((unsigned)(x - 3) < 2u ? kv : 0u) | ((unsigned)(x - 4) < 2u ? kv << 16 : 0u);
  const int q0 = g - 1, q1 = c < 3 ? g : g - 2;
  uint32_t y0a = ub + U_PAD + (q0 & 1) * U_ODD + 16 * (q0 >> 1) + 4 * c;
  uint32_t y1a = ub + U_PAD + (q1 & 1) * U_ODD + 16 * (q1 >> 1) + 4 * c;
  uint32_t f3[3][4][4];
  {
    const uint32_t fa = tb + T_7 + 4 * (16 + x);
#pragma unroll
    for (int tt = 0; tt < 3; tt++)
#pragma unroll
      for (int D = 0; D < 4; D++) {
        const uint32_t a = fa + (tt == 0 ? 316 : (tt == 1 ? 320 : 0)) + 64 * D;
        f3[tt][D][0] = lds32(a); f3[tt][D][1] = lds32(a + 32); f3[tt][D][2] = lds32(a - 32); f3[tt][D][3] = lds32(a);
      }
  }
#pragma unroll
  for (int i = 0; i < 4; i++) asm volatile("" : "+r"(bx[i]), "+r"(by[i]));
  asm volatile("" : "+r"(lb0), "+r"(lb1), "+r"(y0a), "+r"(y1a));
  mbar_wait(BAR(MB_UFULL));
  mbar_wait(BAR(MB_EMPTY + 15));
  TS(36);
  float acc[16][4];
  {
    uint32_t z09[8], z07[8], zm9[8], zm7[8];
#pragma unroll
    for (int i = 0; i < 8; i++) {
      uint32_t h[4];
      ldsm4(h, hb + 128 * i);
      float y0, y1, y2, y3, w0, w1, w2, w3;
      mma0(y0, y1, y2, y3, bx[0], bx[1], bx[2], bx[3], h[2], c < 2 ? h[3] : h[1]);
      mma0(w0, w1, w2, w3, bx[0], bx[1], bx[2], bx[3], h[1], c < 2 ? h[2] : h[0]);
      z09[i] = pack_bf(y0, y1); z07[i] = pack_bf(y2, y3);
      zm9[i] = pack_bf(w0, w1); zm7[i] = pack_bf(w2, w3);
    }
    float a[4][2][4];
#pragma unroll
    for (int kap = 0; kap < 4; kap++)
#pragma unroll
      for (int sg = 0; sg < 2; sg++)
#pragma unroll
        for (int bk = 3; bk >= kap; bk--) {
          const uint32_t(&q0_)[4] = f3[sg ? 2 : 0][bk - kap];
          const uint32_t(&q1_)[4] = f3[sg ? 2 : 1][bk - kap];
          float(&a0)[4] = a[bk][0];
          float(&a1)[4] = a[bk][1];
          if (sg == 0 && kap == 0) {
            mma0(a0[0], a0[1], a0[2], a0[3], q0_[0], q0_[1], q0_[2], q0_[3], z09[0], z09[1]);
            mma0(a1[0], a1[1], a1[2], a1[3], q1_[0], q1_[1], q1_[2], q1_[3], zm9[0], zm9[1]);
          } else {
            mma(a0[0], a0[1], a0[2], a0[3], q0_[0], q0_[1], q0_[2], q0_[3], sg ? zm7[2 * kap] : z09[2 * kap], sg ? zm7[2 * kap + 1] : z09[2 * kap + 1]);
            mma(a1[0], a1[1], a1[2], a1[3], q1_[0], q1_[1], q1_[2], q1_[3], sg ? z07[2 * kap] : zm9[2 * kap], sg ? z07[2 * kap + 1] : zm9[2 * kap + 1]);
          }
        }
    SPLIT();
#pragma unroll
    for (int i = 0; i < 8; i++) {
      uint32_t h[4];
      ldsm4(h, qa + 128 * i);
      const float ci[4] = {a[i >> 1][0][2 * (i & 1)], a[i >> 1][0][2 * (i & 1) + 1], a[i >> 1][1][2 * (i & 1)], a[i >> 1][1][2 * (i & 1) + 1]};
      mmac(acc[8 + i], h[0], h[1], h[2], h[3], lb0, lb1, ci);
    }
  }
  TS(44);
  {
    uint2 a5[10], a3[10];
    const uint32_t aa = tb + T_5 + 4 * (8 + 2 * g - 2 * c);
#pragma unroll
    for (int m = 0; m < 10; m++) { a5[m] = lds64(aa + 32 * m); a3[m] = lds64(aa + 384 + 32 * m); }
    uint32_t x5[12][2], x3[12][2];
    auto ygen = [&](int kap) {
#pragma unroll
      for (int hh = 0; hh < 2; hh++) {
        float y0, y1, y2, y3;
        mma0(y0, y1, y2, y3, by[0], by[1], by[2], by[3], lds32(y0a + 128 * kap + 64 * hh), lds32(y1a + 128 * kap + 64 * hh));
        x5[kap][hh] = pack_bf(y0, y1);
        x3[kap][hh] = pack_bf(y2, y3);
      }
    };
    ygen(11); ygen(10); ygen(9); ygen(8);
#pragma unroll
    for (int kap = 11; kap >= 0; kap--) {
      if (kap >= 4) ygen(kap - 4);
#pragma unroll
      for (int sg = 0; sg < 2; sg++)
#pragma unroll
        for (int i = 4; i >= 0; i--) {
          const int be = kap + 4 + i;
          if (be <= 15) {
            const uint2 &hi = sg ? a3[2 * i + 1] : a5[2 * i + 1], &lo = sg ? a3[2 * i] : a5[2 * i];
            const uint32_t b0 = sg ? x3[kap][0] : x5[kap][0], b1 = sg ? x3[kap][1] : x5[kap][1];
            if (be < 8 && i == 0 && sg == 0) mma0(acc[be][0], acc[be][1], acc[be][2], acc[be][3], hi.x, hi.y, lo.x, lo.y, b0, b1);
            else mma(acc[be][0], acc[be][1], acc[be][2], acc[be][3], hi.x, hi.y, lo.x, lo.y, b0, b1);
          }
        }
    }
  }
  TS(45);
  {
    const uint32_t st = tb + T_ST + lane * 8;
#pragma unroll
    for (int be = 4; be < 12; be++) sts64(st + 256 * be, pack_bf(acc[be][0], acc[be][1]), pack_bf(acc[be][2], acc[be][3]));
    SPLIT();
    uint32_t F[66], qd[8][4];
    const uint32_t fa = tb + T_D + 32 + 4 * x;
#pragma unroll
    for (int i = 0; i < 32; i++) {
      const int s = 120 - (i >> 2) - 8 * (i & 3);
      uint32_t(&q)[4] = qd[i & 7];
      ldsm4(q, qa + 16 * s);
      const int m = 16 * (i & 3) + 2 * (i >> 2);
      F[m] = lds32(fa + 32 * m); F[m + 1] = lds32(fa + 32 * m + 32);
#pragma unroll
      for (int be = 15; be >= 12; be--) {
        const int de = 8 * be - s;
        if (de >= 0) mma(acc[be][0], acc[be][1], acc[be][2], acc[be][3], q[0], q[1], q[2], q[3], F[2 * de + 1], F[2 * de]);
      }
    }
    F[64] = lds32(fa + 32 * 64); F[65] = lds32(fa + 32 * 65);
    uint32_t qp = qa + 128 * 11, sta = st + 256 * 10;
    uint4* yd = ydst + 7 * 32;
#pragma unroll
    for (int i = 0; i < 6; i++) ldsm4(qd[i], qp - 16 * i);
    uint2 sv = lds64(sta + 256);
    float ci[4] = {bf_lo(sv.x), bf_hi(sv.x), bf_lo(sv.y), bf_hi(sv.y)};
    float T[5][4];
#pragma unroll
    for (int i = 0; i < 16; i++) T[i >> 2][i & 3] = acc[12 + (i >> 2)][i & 3];
    nb_sync(NB_YZ, 160);
    TS(46);
#pragma unroll 1
    for (int bp = 5; bp >= 0; bp--) {
      uint32_t held[2];
#pragma unroll
      for (int o = 1; o >= 0; o--) {
#pragma unroll
        for (int k = 4; k >= 1; k--) mmac(T[k], qd[0][0], qd[0][1], qd[0][2], qd[0][3], F[16 * k + 1], F[16 * k], T[k - 1]);
        mmac(T[0], qd[0][0], qd[0][1], qd[0][2], qd[0][3], F[1], F[0], ci);
        ldsm4(qd[6], qp - 16 * 6);
        ldsm4(qd[7], qp - 16 * 7);
        sv = lds64(sta);
#pragma unroll
        for (int i = 1; i < 8; i++) {
#pragma unroll
          for (int k = 3; k >= 0; k--)
            mma(T[k][0], T[k][1], T[k][2], T[k][3], qd[i][0], qd[i][1], qd[i][2], qd[i][3], F[16 * k + 2 * i + 1], F[16 * k + 2 * i]);
          if (i < 7) ldsm4(qd[i - 1], qp - 128 - 16 * (i - 1));
          if (i == 2) {
            const uint32_t w0 = pack_bf(T[4][0], T[4][1]), w1 = pack_bf(T[4][2], T[4][3]);
            if (o) { held[0] = w0; held[1] = w1; }
            else st_x(yd, nz(w0), w1, held[0], held[1]);
          }
          if (i == 4) {
            if (2 * bp + o <= 4) sv = make_uint2(0, 0);
            ci[0] = bf_lo(sv.x); ci[1] = bf_hi(sv.x); ci[2] = bf_lo(sv.y); ci[3] = bf_hi(sv.y);
          }
        }
        qp -= 128; sta -= 256;
      }
      yd -= 32;
    }
#pragma unroll
    for (int B = 1; B >= 0; B--)
      st_x(ydst + B * 32, nz(pack_bf(T[2 * B][0], T[2 * B][1])), pack_bf(T[2 * B][2], T[2 * B][3]),
           pack_bf(T[2 * B + 1][0], T[2 * B + 1][1]), pack_bf(T[2 * B + 1][2], T[2 * B + 1][3]));
  }
}

__device__ __forceinline__ void dual_exp(const uint32_t* w, uint32_t* e) {
  const float L = 1.44268798828125f;
  uint32_t mx = bmax2(bmax2(w[0], w[1]), bmax2(w[2], w[3]));
  uint32_t mn = bmin2(bmin2(w[0], w[1]), bmin2(w[2], w[3]));
  mx = bmax2(mx, __shfl_xor_sync(0xffffffffu, mx, 1));
  mn = bmin2(mn, __shfl_xor_sync(0xffffffffu, mn, 1));
  mx = bmax2(mx, __shfl_xor_sync(0xffffffffu, mx, 2));
  mn = bmin2(mn, __shfl_xor_sync(0xffffffffu, mn, 2));
  const float mx0 = bf_lo(mx) * -L, mx1 = bf_hi(mx) * -L, mn0 = bf_lo(mn) * L, mn1 = bf_hi(mn) * L;
#pragma unroll
  for (int i = 0; i < 2; i++) {
    const float a0 = bf_lo(w[2 * i]), a1 = bf_hi(w[2 * i]), b0 = bf_lo(w[2 * i + 1]), b1 = bf_hi(w[2 * i + 1]);
    e[2 * i] = pack_bf(ex2(fmaf(a0, L, mx0)), ex2(fmaf(b0, L, mx0)));
    e[2 * i + 1] = pack_bf(ex2(fmaf(a1, L, mx1)), ex2(fmaf(b1, L, mx1)));
    e[4 + 2 * i] = pack_bf(ex2(fmaf(a0, -L, mn0)), ex2(fmaf(b0, -L, mn0)));
    e[5 + 2 * i] = pack_bf(ex2(fmaf(a1, -L, mn1)), ex2(fmaf(b1, -L, mn1)));
  }
}
__device__ __forceinline__ void norm_store(const uint32_t* e, const float (&s)[4], uint32_t dst) {
  const uint32_t r = pack_bf(rcp(s[0]), rcp(s[2]));
  const __nv_bfloat162 rr = *(const __nv_bfloat162*)&r;
  uint32_t o[4];
#pragma unroll
  for (int i = 0; i < 4; i++) {
    const __nv_bfloat162 v = __hmul2(*(const __nv_bfloat162*)&e[i], (i & 1) ? __high2bfloat162(rr) : __low2bfloat162(rr));
    o[i] = *(const uint32_t*)&v;
  }
  stsm4(dst, o[0], o[1], o[2], o[3]);
}
__host__ __device__ constexpr uint64_t qdesc(uint32_t addr) { return mkdesc(addr, 128, 256, 0); }

__global__ void __launch_bounds__(NTHREADS, 1)
fused_kernel(const Params P, const __grid_constant__ CUtensorMap mx, const __grid_constant__ CUtensorMap mw,
             const __grid_constant__ CUtensorMap mo, const __grid_constant__ CUtensorMap mu,
             const __grid_constant__ CUtensorMap mout, const __grid_constant__ CUtensorMap mw4) {
  constexpr uint32_t sb = SB;
  const int tid = threadIdx.x, lane = tid & 31;
  const int warp = __shfl_sync(0xffffffffu, tid >> 5, 0);
  const int b = blockIdx.x, oct = b >> 3, i8 = b & 7;
  const int rt = oct < 8 ? oct : 15 - oct;
  const int hp = (oct >> 3) * 8 + i8;

  const int wg = warp >> 2, w = warp & 3;
  const int d = b * 4 + ((tid >> 5) & 3);
  if (tid < 384) {
    asm volatile("prefetch.tensormap [%0];" ::"l"(&mu) : "memory");
    asm volatile("prefetch.tensormap [%0];" ::"l"(&mw) : "memory");
    asm volatile("prefetch.tensormap [%0];" ::"l"(&mx) : "memory");
    asm volatile("prefetch.tensormap [%0];" ::"l"(&mw4) : "memory");
  }
  if (warp == 12) {
    if (lane == 0) {
#pragma unroll
      for (int i = 0; i < 9; i++) mbar_init(BAR(i), 1);
      asm volatile("fence.mbarrier_init.release.cluster;" ::: "memory");
    }
    __syncwarp();
    if (lane < 9) mbar_expect(BAR(0) + 8 * lane, lane == 5 ? 65536 : ((lane == 0 || lane > 5) ? 16384 : 28672));
    __syncwarp();
    e_tma3d(sb + OFF_W, &mw, BAR(MB_FULL), hp * 32, 0, 0);
    e_tma2d(sb + OFF_X + 3 * 16384, &mx, BAR(MB_FULL), 0, rt * 256);
  } else if (warp == 13) {
    if (lane == 0) {
#pragma unroll
      for (int i = 9; i < 39; i++) mbar_init(BAR(i), i < MB_EMPTY ? 1 : (i < MB_AUX ? 4 : 9));
      asm volatile("fence.mbarrier_init.release.cluster;" ::: "memory");
    }
    __syncwarp();
    if (lane < 9) mbar_expect(BAR(MB_FULL + 8) + 8 * lane, lane < 8 ? 16384 : 131072);
  }
  const KgenRaw raw = kgen_load(P, d, tid >> 7, lane);
  const unsigned short dsk = __ldg((const unsigned short*)P.Dskip + d);
  const uint32_t tb = sb + OFF_T + w * T_CH;
  const uint32_t kp = wg >= 2 ? sb + OFF_STG0 + 16384 + w * 2048 : ((tb + 127) & ~127u) + wg * 2048;
  const KgenAddr kad = kgen_addr(lane, wg == 3 ? sb + OFF_X + 32768 + w * 2048 : kp);
  if (warp == 12) {
#pragma unroll 1
    for (int kb = 1; kb < 4; kb++) {
      if (kb == U_AT) e_tma5d(sb + OFF_STG0, &mu, BAR(MB_URAW), i8 * 64, oct * 4);
      e_tma3d(sb + OFF_W + kb * 12288, &mw, BAR(MB_FULL) + 8 * kb, hp * 32, kb * 64, 0);
      e_tma2d(sb + OFF_X + (kb < 2 ? kb + 3 : kb - 2) * 16384, &mx, BAR(MB_FULL) + 8 * kb, kb * 64, rt * 256);
    }
    e_prefetch(P.x + (size_t)(rt * 256 + hp * 16) * 512, 16384);
    e_tma4d(sb + OFF_W + 4 * 12288, &mw4, BAR(MB_FULL + 4), hp * 32, 4);
    if (smem_u32(smem_raw) != SB) __trap();
    if (lane == 0) TS1(54);
  }
  float k[5][4], k2048, ksc;
  kgen_unit(raw, kad, blockIdx.y, k, k2048, ksc);
  TS(40 + wg);
  if ((fu(k[0][0]) & fu(k[1][0]) & fu(k[2][0]) & fu(k[3][0]) & fu(k[4][0])) == 0xffffffffu) sts32(kp, 0);
  if (wg == 3) {
    nb_sync(0, 512);
    if (warp == 12) {
      asm volatile("fence.proxy.async.shared::cta;" ::: "memory");
      e_tma2d(sb + OFF_X + 2 * 16384, &mx, BAR(MB_FULL + 4), 256, rt * 256);
    }
  } else if (wg) {
    nb_arrive(0, 512);
  }
  k2048 += __shfl_xor_sync(0xffffffffu, k2048, 16);
  k2048 += __shfl_xor_sync(0xffffffffu, k2048, 8);
  if (wg != 2) {
    uint32_t h[10];
#pragma unroll
    for (int j = 0; j < 10; j++) h[j] = hu(__floats2half2_rn(k[j >> 1][2 * (j & 1)], k[j >> 1][2 * (j & 1) + 1]));
    sts128(kp + lane * 16, h[0], h[1], h[2], h[3]);
    sts128(kp + 512 + lane * 16, h[4], h[5], h[6], h[7]);
    sts128(kp + 1024 + lane * 16, h[8], h[9], fu(k2048), fu(ksc));
  }
  if (wg == 0) { nb_arrive(NB_PREP, 512); nb_sync(0, 512); }
  else if (wg == 3) nb_arrive(NB_PREP, 512);
  else nb_sync(NB_PREP, 512);
  if (warp >= 12) {
    asm volatile("setmaxnreg.dec.sync.aligned.u32 32;");
    if (warp == 12) {
      uint32_t slot = sb + OFF_X + 3 * 16384;
#pragma unroll 1
      for (int n = 0; n < 11; n++) {
        mbar_spin(BAR(MB_EMPTY) + 8 * n);
        const int m = n + 5;
        e_tma2d(slot, &mx, BAR(MB_FULL) + 8 * m, (m & 7) * 64, rt * 256 + (m >> 3) * 128);
        slot = slot == sb + OFF_X + 4 * 16384 ? sb + OFF_X : slot + 16384;
        if (n == 7) e_prefetch(P.wo + (size_t)b * 2048, 4096);
      }
#pragma unroll 1
      for (int i = 0; i < 8; i++) {
        mbar_wait(BAR(MB_EMPTY + 10) + 8 * ((0x54332100u >> (4 * i)) & 7));
        const int w0 = (0x54736210u >> (4 * i)) & 7;
        e_tma3d(sb + OFF_W + w0 * 16384, &mo, BAR(MB_WO), 0, w0 * 64, (hp & 3) * 2);
      }
    } else {
      if (warp == 15) {
        const uint4 v0 = __ldg((const uint4*)P.wphi + hp * 64 + lane), v1 = __ldg((const uint4*)P.wphi + hp * 64 + 32 + lane);
        sts128(sb + OFF_PHI + (lane & 1) * 256 + (lane >> 1) * 16, v0.x, v0.y, v0.z, v0.w);
        sts128(sb + OFF_PHI + 512 + (lane & 1) * 256 + (lane >> 1) * 16, v1.x, v1.y, v1.z, v1.w);
        const uint32_t one = (((lane >> 3) ^ (lane >> 4)) & 1) ? 0u : ((lane & 1) ? 0x3F800000u : 0x3F80u);
        const int q = (lane >> 1) & 3;
        sts128(sb + OFF_EYE + lane * 16, q == 0 ? one : 0u, q == 1 ? one : 0u, q == 2 ? one : 0u, q == 3 ? one : 0u);
        sts64(sb + OFF_ONE + lane * 8, 0x3F803F80u, 0x3F803F80u);
        asm volatile("fence.proxy.async.shared::cta;" ::: "memory");
        __syncwarp();
        if (lane == 0) mbar_arrive(BAR(MB_AUX));
        mbar_wait(BAR(MB_EMPTY + ZERO_STEP));
        uint4* py = P.xs + X_Y + b * 1024 + lane;
#pragma unroll 1
        for (int i = 0; i < 1024; i += 32) st_x(py + i, 0, 0, 0, 0);
        nb_arrive(NB_YZ, 160);
        nb_arrive(NB_ODONE, 320);
        if (lane == 0) TS1(55);
        return;
      }
      uint32_t* const cnt = (uint32_t*)(P.xs + X_CNT) + (warp == 13 ? i8 : 8 + rt) * 32;
      const unsigned target = (ld_x32(cnt) & ~15u) + 16;
      if (warp == 13) {
        uint4* pp = P.xs + X_PART + (hp * 8 + rt) * 144 + lane;
#pragma unroll 1
        for (int i = 0; i < 144; i += 32) if (i + lane < 144) st_x(pp + i, 0, 0, 0, 0);
      }
      nb_sync(warp == 13 ? NB_INIT : NB_ODONE, warp == 13 ? 160 : 320);
      if (lane == 0) TS1(warp == 13 ? 49 : 56);
      asm volatile("fence.proxy.async.shared::cta;" ::: "memory");
      if (lane == 0) asm volatile("red.release.gpu.global.add.u32 [%0], 1;" ::"l"(cnt) : "memory");
      if (lane == 0) TS1(warp == 13 ? 50 : 57);
      const uint32_t* pc = (warp == 13 && (lane & 1)) ? (uint32_t*)(P.xs + X_CNT) + (b >> 4) * 32 : cnt;
#pragma unroll 1
      for (int i = 0; i < SPIN_MAX; i++) {
        unsigned v;
        asm volatile("ld.acquire.gpu.global.u32 %0, [%1];" : "=r"(v) : "l"(pc) : "memory");
        if (__all_sync(0xffffffffu, (int)(v - target) >= 0)) break;
      }
      if (lane == 0) TS1(warp == 13 ? 51 : 58);
      asm volatile("fence.proxy.async.global;" ::: "memory");
      if (warp == 13) {
        mbar_wait(BAR(MB_EMPTY + 11));
        e_expect(BAR(MB_UFULL), 4 * U_CH);
        e_bulk(sb + OFF_U, P.xs + X_UT + b * (U_CH / 4), 4 * U_CH, BAR(MB_UFULL));
      } else {
        const uint4* src = P.xs + X_O + (rt * 4 + (hp >> 2)) * 4096;
        e_expect(BAR(MB_OA), 14336);
        e_bulk(sb + OFF_STG0, src + 3200, 14336, BAR(MB_OA));
        e_expect(BAR(MB_OC), 32768);
        e_bulk(sb + OFF_X + 32768, src, 32768, BAR(MB_OC));
        nb_sync(NB_BDONE, 288);
        asm volatile("fence.proxy.async.shared::cta;" ::: "memory");
        e_expect(BAR(MB_OB), 18432);
        e_bulk(sb + OFF_U, src + 2048, 18432, BAR(MB_OB));
      }
    }
    return;
  }

  const int t = tid & 127;
  const int g = lane >> 2, c = lane & 3;
  {
    if (wg == 2) {
      asm volatile("setmaxnreg.inc.sync.aligned.u32 160;");
#pragma unroll
      for (int j = 0; j < 5; j++) { k[j][0] *= ksc; k[j][1] *= ksc; k[j][2] *= ksc; k[j][3] *= ksc; }
#pragma unroll 1
      for (int q = 0; q < 3; q++) {
        const uint32_t src = (q == 2 ? kp : ((tb + 127) & ~127u) + q * 2048) + lane * 16;
        const uint4 v0 = lds128(src), v1 = lds128(src + 512), v2 = lds128(src + 1024);
        const uint32_t h[10] = {v0.x, v0.y, v0.z, v0.w, v1.x, v1.y, v1.z, v1.w, v2.x, v2.y};
#pragma unroll
        for (int j = 0; j < 10; j++) {
          const float2 f = __half22float2(*(const __half2*)&h[j]);
          k[j >> 1][2 * (j & 1)] = fmaf(f.x, uf(v2.w), k[j >> 1][2 * (j & 1)]);
          k[j >> 1][2 * (j & 1) + 1] = fmaf(f.y, uf(v2.w), k[j >> 1][2 * (j & 1) + 1]);
        }
        k2048 += uf(v2.z);
      }
#pragma unroll
      for (int o2 = 4; o2; o2 >>= 1) k2048 += __shfl_xor_sync(0xffffffffu, k2048, o2);
      if (lane == 0) k[0][0] += bf_lo(dsk);
      __syncwarp();
      if (lane == 0) mbar_arrive(BAR(MB_AUX));
      TS(34);
      build_tables(tb, lane, k, k2048);
      TS(35);
      uint4* const g_y = P.xs + X_Y;
      conv_channel(sb + OFF_U + w * U_CH, tb, lane, g_y + (size_t)d * 256 + lane);
      nb_arrive(NB_BDONE, 288);
      TS(37);
      mbar_wait(BAR(MB_OA));
      const int lam = w * 8 + g;
      const uint4* src = g_y + (size_t)(oct * 32 + c * 8) * 256 + i8 * 32 + lam;
      uint4 v[8];
#pragma unroll 1
      for (int it = 0; it < SPIN_MAX; it++) {
        uint32_t m = 0xffffffffu;
#pragma unroll
        for (int i = 0; i < 8; i++) v[i] = ld_x(src + i * 256);
#pragma unroll
        for (int i = 0; i < 8; i++) m = min(m, v[i].x);
        if (__all_sync(0xffffffffu, m != 0)) break;
      }
      __nv_bfloat16* dst = P.out + (size_t)(i8 * 256 + (lam >> 2) * 16 + (lam & 3) * 2) * 1024 + 512 + oct * 32 + c * 8;
#pragma unroll
      for (int i = 0; i < 8; i++) *(uint4*)(dst + (size_t)((i >> 2) * 128 + ((i >> 1) & 1) * 8 + (i & 1)) * 1024) = tr_row(v, i);
      TS(38);
      GT(63);
      if (w == 0) TSDUMP(32);
      return;
    }
    if (wg == 1) {
      mbar_wait(BAR(MB_URAW));
      TS(48);
      uint4* dst = P.xs + X_UT + (i8 * 64 + g) * (U_CH / 16) + (c & 1) * (U_ODD / 16) + U_PAD / 16 + oct * 8 + w * 2 + (c >> 1);
      uint32_t r[8][4];
#pragma unroll
      for (int i = 0; i < 8; i++) ldsm4t(r[i], sb + OFF_STG0 + w * 4096 + lane * 128 + (((i ^ lane) & 7) << 4));
#pragma unroll
      for (int i = 0; i < 8; i++) dst[i * (U_CH / 2)] = make_uint4(r[i][0], r[i][1], r[i][2], r[i][3]);
      nb_arrive(NB_INIT, 160);
      if (lane == 0) mbar_arrive(BAR(MB_AUX));
      mbar_wait(BAR(MB_EMPTY + 4));
      mbar_spin(BAR(MB_EMPTY + 6));
    }
    TS(wg * 16 + 1);
  }

  float acc[2][48];
  {
    uint32_t fb = BAR(MB_FULL) + 64 * wg;
    uint32_t da = (uint32_t)mkdesc(sb + OFF_X, 16, 0, 0) + (wg ? 1024 : 3072), db = (uint32_t)mkdesc(sb + OFF_W, 4096, 0, 0);
    constexpr uint64_t ha = mkdesc(0, 0, 1024, 1), hb = mkdesc(0, 0, 512, 2);
#pragma unroll 1
    for (int kb = 0; kb < 8; kb++) {
      mbar_spin(fb);
      if (kb == 0) TS(wg * 16 + 2);
      WG_FENCE();
#pragma unroll
      for (int k = 0; k < 4; k++) {
        wgmma_ss_n96(acc[0], ha | (da + 2 * k), hb | (db + 64 * k), k ? 1 : kb);
        wgmma_ss_n96(acc[1], ha | (da + 2 * k + 512), hb | (db + 64 * k), k ? 1 : kb);
      }
      WG_COMMIT();
      WG_WAIT(1);
      if (kb > 0 && lane == 0) mbar_arrive(fb + 8 * (MB_EMPTY - MB_FULL - 1));
      fb += 8; db += 768;
      da = da == (uint32_t)mkdesc(sb + OFF_X + 65536, 16, 0, 0) ? da - 4096 : da + 1024;
    }
    WG_WAIT(0);
    if (lane == 0) mbar_arrive(fb + 8 * (MB_EMPTY - MB_FULL - 1));
    mbar_spin(fb + 8 * (MB_EMPTY - MB_FULL - 1));
  }
  TS(wg * 16 + 3);
  asm volatile("setmaxnreg.inc.sync.aligned.u32 160;");

  constexpr uint32_t stg0 = sb + OFF_STG0, stg1 = sb + OFF_X + 32768;
  const uint32_t sl = (wg ? stg1 : stg0) + w * SLAB + lane * 16;
  uint32_t pw[32], eq[32], vp[16];
  {
    uint4 af[8];
#pragma unroll
    for (int u = 0; u < 8; u++) {
      const float* a = acc[(u >> 1) & 1] + (u < 4 ? 16 : 0) + 8 * (u & 1);
      af[u] = make_uint4(pack_bf(a[0], a[1]), pack_bf(a[2], a[3]), pack_bf(a[4], a[5]), pack_bf(a[6], a[7]));
    }
    mbar_wait(BAR(MB_AUX));
    float p[8][8];
    WG_FENCE();
#pragma unroll
    for (int u = 0; u < 8; u++) wgmma_rs_n16(p[u], af[u], qdesc(sb + OFF_PHI + (u & 1) * 512), 0);
    WG_COMMIT();
#pragma unroll
    for (int i = 0; i < 16; i++) vp[i] = pack_bf(acc[i >> 3][32 + 2 * (i & 7)], acc[i >> 3][33 + 2 * (i & 7)]);
    WG_WAIT(0);
#pragma unroll
    for (int u = 0; u < 8; u++) {
      pw[4 * u] = pack_bf(p[u][0], p[u][2]); pw[4 * u + 1] = pack_bf(p[u][1], p[u][3]);
      pw[4 * u + 2] = pack_bf(p[u][4], p[u][6]); pw[4 * u + 3] = pack_bf(p[u][5], p[u][7]);
    }
  }
  uint4* const g_part = P.xs + X_PART;
  uint4* const g_o = P.xs + X_O;
  constexpr uint32_t kvs = stg0;
#pragma unroll 1
  for (int it = 0; it < 2; it++) {
#pragma unroll
    for (int u = 0; u < 4; u++) dual_exp(pw + 4 * u, eq + 8 * u);
    if (it == 0) {
      TS(wg * 16 + 12);
      float rs[8][4];
      WG_FENCE();
#pragma unroll
      for (int i = 0; i < 8; i++) wgmma_rs_n8(rs[i], make_uint4(eq[4 * i], eq[4 * i + 1], eq[4 * i + 2], eq[4 * i + 3]), qdesc(sb + OFF_ONE), 0);
      WG_COMMIT();
#pragma unroll
      for (int i = 0; i < 4; i++) stsm4(sl + (i >> 1) * 4 * SLAB + 2048 + (i & 1) * 512, vp[4 * i], vp[4 * i + 1], vp[4 * i + 2], vp[4 * i + 3]);
      sts128(sl + (lane >> 4) * (4 * SLAB - 256) + 3072, 0x3F803F80u, 0x3F803F80u, 0x3F803F80u, 0x3F803F80u);
      WG_WAIT(0);
#pragma unroll
      for (int i = 0; i < 8; i++) norm_store(eq + 4 * i, rs[i], sl + (i >> 2) * 4 * SLAB + (i & 3) * 512);
      asm volatile("fence.proxy.async.shared::cta;" ::: "memory");
      if (wg) {
        nb_arrive(NB_ST0, 256);
      } else {
        float kc[20];
#pragma unroll 1
        for (int j = 0; j < 2; j++) {
          nb_sync(j ? NB_ST0 : NB_WG0, j ? 256 : 128);
          const uint64_t da = qdesc(stg0) - j * ((stg0 - stg1) >> 4);
          WG_FENCE();
#pragma unroll
          for (int s = 0; s < 8; s++) wgmma_ss_n40(kc, da + s * (SLAB >> 4), da + s * (SLAB >> 4) + 128, s ? 1 : j);
          WG_COMMIT();
          WG_WAIT(0);
          TS(6);
        }
        mbar_wait(BAR(MB_UFULL));
        float kv[12];
#pragma unroll
        for (int i = 0; i < 8; i++) kv[i] = w & 2 ? kc[8 + i] : kc[i];
        kv[8] = kc[16]; kv[10] = kc[18];
        uint4* pp = g_part + (size_t)(hp * 8 + rt) * 144;
        st_x(pp + t, nz(pack_bf(kv[0], kv[1])), pack_bf(kv[2], kv[3]), pack_bf(kv[4], kv[5]), pack_bf(kv[6], kv[7]));
        if (c < 2) st_x32((uint32_t*)(pp + 128) + w * 16 + c * 8 + g, nz(fu(c ? kv[10] : kv[8])));
        TS(5);
      }
#pragma unroll
      for (int i = 0; i < 16; i++) pw[i] = pw[i + 16];
    }
  }
  TS(wg * 16 + 4);
  if (wg == 1) {
    mbar_wait(BAR(MB_UFULL));
    const uint4* ps = g_part + (size_t)hp * 8 * 144 + t;
    const uint32_t* zs = (const uint32_t*)(g_part + (size_t)(hp * 8 + (lane >> 4) * 4) * 144 + 128) + w * 16 + (lane & 15);
    uint4 v[8];
    uint32_t zv[4];
#pragma unroll 1
    for (int it = 0; it < SPIN_MAX; it++) {
#pragma unroll
      for (int i = 0; i < 8; i++) v[i] = ld_x(ps + i * 144);
#pragma unroll
      for (int i = 0; i < 4; i++) zv[i] = ld_x32(zs + i * 576);
      uint32_t m = min(min(zv[0], zv[1]), min(zv[2], zv[3]));
#pragma unroll
      for (int i = 0; i < 8; i++) m = min(m, v[i].x);
      if (__all_sync(0xffffffffu, m != 0)) break;
    }
    float s[8];
    WG_FENCE();
#pragma unroll
    for (int r = 0; r < 8; r++) wgmma_rs_n16(s, v[r], qdesc(sb + OFF_EYE), r);
    WG_COMMIT();
    float zsum = (uf(zv[0]) + uf(zv[1])) + (uf(zv[2]) + uf(zv[3]));
    zsum += __shfl_xor_sync(0xffffffffu, zsum, 16);
    const uint32_t z1 = pack_bf(zsum, 1.f);
    if (lane < 16) sts128(kvs + w * 768 + 512 + lane * 16, z1, z1, z1, z1);
    WG_WAIT(0);
    stsm4(kvs + w * 768 + lane * 16, pack_bf(s[0], s[1]), pack_bf(s[2], s[3]), pack_bf(s[4], s[5]), pack_bf(s[6], s[7]));
    asm volatile("fence.proxy.async.shared::cta;" ::: "memory");
    TS(22);
  }
  nb_sync(NB_KV, 256);
  {
    float n[8][12];
    WG_FENCE();
#pragma unroll
    for (int i = 0; i < 8; i++) wgmma_rs_n24(n[i], make_uint4(eq[4 * i], eq[4 * i + 1], eq[4 * i + 2], eq[4 * i + 3]), qdesc(kvs + (i & 3) * 768), 0);
    WG_COMMIT();
    uint32_t* od = (uint32_t*)(g_o + (size_t)((rt * 4 + wg * 2) * 32 + hp * 2) * 128) + w * 64 + lane;
    WG_WAIT(0);
#pragma unroll
    for (int u = 0; u < 4; u++) {
      float(&np)[12] = n[2 * u];
      const float(&nm)[12] = n[2 * u + 1];
      const float q0 = np[9] * rcp(nm[9]), q1 = np[11] * rcp(nm[11]);
      const float r0 = rcp(fmaf(nm[8], q0, fmaf(np[9], 1e-6f, np[8]))), r1 = rcp(fmaf(nm[10], q1, fmaf(np[11], 1e-6f, np[10])));
#pragma unroll
      for (int i = 0; i < 8; i++) np[i] = fmaf(nm[i], (i & 2) ? q1 : q0, np[i]);
      uint32_t* o = od + (u >> 1) * 16384 + (u & 1) * 512;
      o[0] = pack_bf(np[0] * r0, np[1] * r0);
      o[32] = pack_bf(np[2] * r1, np[3] * r1);
      o[256] = pack_bf(np[4] * r0, np[5] * r0);
      o[288] = pack_bf(np[6] * r1, np[7] * r1);
    }
  }
  TS(wg * 16 + 7);
  nb_arrive(NB_ODONE, 320);
  if (wg) { if (w == 0) TSDUMP(16); return; }
  mbar_wait(BAR(MB_WO));
  mbar_wait(BAR(MB_OA));
  TS(8);
  nb_sync(NB_BDONE, 288);
  TS(9);
  float oc[64];
  {
    constexpr uint64_t ha = mkdesc(0, 0, 128, 0), hb = mkdesc(0, 0, 1024, 1);
    constexpr uint32_t da0 = (uint32_t)mkdesc(stg1, 1024, 0, 0), db0 = (uint32_t)mkdesc(sb + OFF_W, 8192, 0, 0);
#pragma unroll 1
    for (int j = 0; j < 8; j++) {
      const int kb = (j + 7) & 7;
      if ((j & 3) == 1) mbar_spin(j == 1 ? BAR(MB_OC) : BAR(MB_OB));
      WG_FENCE();
#pragma unroll
      for (int k = 0; k < 4; k++) wgmma_ss_n128(oc, ha | (da0 + 512 * kb + 128 * k), hb | (db0 + 1024 * kb + 128 * k), k ? 1 : j);
      WG_COMMIT();
    }
    WG_WAIT(0);
  }
  TS(10);
  nb_sync(NB_WG0, 128);
  const uint32_t ot = sb + OFF_W + w * 4096;
#pragma unroll
  for (int i = 0; i < 16; i += 2)
    stsm4(ot + (i >> 3) * 2048 + (lane & 15) * 128 + (((i + (lane >> 4)) ^ lane) & 7) * 16, pack_bf(oc[4 * i], oc[4 * i + 1]),
          pack_bf(oc[4 * i + 2], oc[4 * i + 3]), pack_bf(oc[4 * i + 4], oc[4 * i + 5]), pack_bf(oc[4 * i + 6], oc[4 * i + 7]));
  asm volatile("fence.proxy.async.shared::cta;" ::: "memory");
  __syncwarp();
  e_store3d(&mout, ot, (rt * 4 + (hp >> 2)) * 64 + w * 16, (hp & 3) * 2);
  TS(wg * 16 + 11);
  GT(61 + wg);
  if (w == 0) TSDUMP(0);
  if (w == 1) TSDUMP(48);
}

typedef CUresult (*EncodeFn)(CUtensorMap*, CUtensorMapDataType, cuuint32_t, void*, const cuuint64_t*, const cuuint64_t*,
                             const cuuint32_t*, const cuuint32_t*, CUtensorMapInterleave, CUtensorMapSwizzle,
                             CUtensorMapL2promotion, CUtensorMapFloatOOBfill);

}

extern "C" void kernel_launch(void* const* d_in, const int* in_sizes, int n_in, void* d_out, int out_size) {
  (void)in_sizes; (void)n_in; (void)out_size;
  void* fn = nullptr;
  cudaDriverEntryPointQueryResult qr;
  cudaGetDriverEntryPoint("cuTensorMapEncodeTiled", &fn, cudaEnableDefault, &qr);
  EncodeFn enc = (EncodeFn)fn;
  CUtensorMap mx, mw, mo, mu, mout, mw4;
  const cuuint32_t es[5] = {1, 1, 1, 1, 1};
  {
    cuuint64_t dims[2] = {512, 2048}, st[1] = {1024};
    cuuint32_t box[2] = {64, 128};
    enc(&mx, CU_TENSOR_MAP_DATA_TYPE_BFLOAT16, 2, d_in[0], dims, st, box, es, CU_TENSOR_MAP_INTERLEAVE_NONE,
        CU_TENSOR_MAP_SWIZZLE_128B, CU_TENSOR_MAP_L2_PROMOTION_L2_128B, CU_TENSOR_MAP_FLOAT_OOB_FILL_NONE);
  }
  {
    cuuint64_t dims[3] = {512, 512, 3}, st[2] = {3072, 1024};
    cuuint32_t box[3] = {32, 64, 3};
    enc(&mw, CU_TENSOR_MAP_DATA_TYPE_BFLOAT16, 3, d_in[1], dims, st, box, es, CU_TENSOR_MAP_INTERLEAVE_NONE,
        CU_TENSOR_MAP_SWIZZLE_64B, CU_TENSOR_MAP_L2_PROMOTION_L2_128B, CU_TENSOR_MAP_FLOAT_OOB_FILL_NONE);
  }
  {
    cuuint64_t dims[3] = {64, 512, 8}, st[2] = {1024, 128};
    cuuint32_t box[3] = {64, 64, 2};
    enc(&mo, CU_TENSOR_MAP_DATA_TYPE_BFLOAT16, 3, d_in[3], dims, st, box, es, CU_TENSOR_MAP_INTERLEAVE_NONE,
        CU_TENSOR_MAP_SWIZZLE_128B, CU_TENSOR_MAP_L2_PROMOTION_L2_128B, CU_TENSOR_MAP_FLOAT_OOB_FILL_NONE);
  }
  {
    cuuint64_t dims[5] = {512, 2, 4, 4, 64}, st[4] = {1024, 8192, 2048, 32768};
    cuuint32_t box[5] = {64, 2, 4, 4, 4};
    enc(&mu, CU_TENSOR_MAP_DATA_TYPE_BFLOAT16, 5, d_in[4], dims, st, box, es, CU_TENSOR_MAP_INTERLEAVE_NONE,
        CU_TENSOR_MAP_SWIZZLE_128B, CU_TENSOR_MAP_L2_PROMOTION_L2_128B, CU_TENSOR_MAP_FLOAT_OOB_FILL_NONE);
  }
  {
    cuuint64_t dims[3] = {64, 2048, 16}, st[2] = {2048, 128};
    cuuint32_t box[3] = {64, 16, 2};
    enc(&mout, CU_TENSOR_MAP_DATA_TYPE_BFLOAT16, 3, d_out, dims, st, box, es, CU_TENSOR_MAP_INTERLEAVE_NONE,
        CU_TENSOR_MAP_SWIZZLE_128B, CU_TENSOR_MAP_L2_PROMOTION_NONE, CU_TENSOR_MAP_FLOAT_OOB_FILL_NONE);
  }
  {
    cuuint64_t dims[4] = {512, 64, 3, 8}, st[3] = {3072, 1024, 64 * 3072};
    cuuint32_t box[4] = {32, 64, 3, 4};
    enc(&mw4, CU_TENSOR_MAP_DATA_TYPE_BFLOAT16, 4, d_in[1], dims, st, box, es, CU_TENSOR_MAP_INTERLEAVE_NONE,
        CU_TENSOR_MAP_SWIZZLE_64B, CU_TENSOR_MAP_L2_PROMOTION_L2_128B, CU_TENSOR_MAP_FLOAT_OOB_FILL_NONE);
  }
  Params P;
  P.x = (const __nv_bfloat16*)d_in[0];
  P.wphi = (const __nv_bfloat16*)d_in[2];
  P.wo = (const __nv_bfloat16*)d_in[3];
  P.logA = (const __nv_bfloat16*)d_in[5];
  P.Aim = (const __nv_bfloat16*)d_in[6];
  P.Cre = (const __nv_bfloat16*)d_in[7];
  P.Cim = (const __nv_bfloat16*)d_in[8];
  P.logdt = (const __nv_bfloat16*)d_in[9];
  P.Dskip = (const __nv_bfloat16*)d_in[10];
  P.out = (__nv_bfloat16*)d_out;
  cudaGetSymbolAddress((void**)&P.xs, g_x);
  P.ts = nullptr;
  cudaFuncSetAttribute(fused_kernel, cudaFuncAttributeMaxDynamicSharedMemorySize, SMEM_BYTES);
  fused_kernel<<<NCTA, NTHREADS, SMEM_BYTES>>>(P, mx, mw, mo, mu, mout, mw4);
}
```

```cpp
#include <cuda_runtime.h>
#include <cuda_bf16.h>
#include <cuda_fp16.h>
#include <cuda.h>
#include <stdint.h>

#define DBG_TS 0

namespace {

constexpr int NTHREADS = 512;
constexpr int NCTA = 128;
constexpr int OFF_W = 0;
constexpr int OFF_X = 98304;
constexpr int OFF_U = OFF_X + 65536;
constexpr int U_CH = 4416, U_ODD = 2240, U_PAD = 128;
constexpr int OFF_STG0 = OFF_U + 18432;
constexpr int SLAB = 3328;
constexpr int OFF_T = OFF_STG0 + 8 * SLAB;
constexpr int T_CH = 5216;
constexpr int T_D = 0;
constexpr int T_5 = 2144;
constexpr int T_3 = T_5 + 384;
constexpr int T_7 = T_5 + 1024;
constexpr int T_9 = T_7 + 320;
constexpr int T_KC = T_9 + 320;
constexpr int T_ST = T_5 - 1024;
constexpr int OFF_PHI = OFF_T + 4 * T_CH;
constexpr int OFF_EYE = OFF_PHI + 1024, OFF_ONE = OFF_EYE + 512;
constexpr int OFF_BAR = OFF_ONE + 256;
constexpr int SMEM_BYTES = OFF_BAR + 512 + 256 * DBG_TS;
constexpr uint32_t SB = 1024;
static_assert(T_KC + 2 * 656 <= T_CH, "table size");
static_assert(SMEM_BYTES <= 232448, "smem");
constexpr int MB_URAW = 0, MB_FULL = 1  , MB_WO = 17, MB_UFULL = 18, MB_OA = 19, MB_OB = 20, MB_OC = 21,
              MB_EMPTY = 22  , MB_AUX = 38;
__host__ __device__ constexpr uint32_t BAR(int i) { return SB + OFF_BAR + 8 * i; }
constexpr int NB_WG0 = 1, NB_ODONE = 2, NB_ST0 = 3  , NB_KV = 5, NB_YZ = 6, NB_INIT = 7, NB_PREP = 8, NB_PROD = 9, NB_KREAD = 10, NB_BDONE = 11, NB_ZERO = 12;
#define U_AT 2
#define ZERO_STEP 15
constexpr int SPIN_MAX = 1 << 16;

constexpr int X_CNT = 0;
constexpr int X_PART = 128;
constexpr int X_O = X_PART + 16 * 8 * 144;
constexpr int X_Y = X_O + 32 * 32 * 128;
constexpr int X_UT = X_Y + 512 * 8 * 32;
constexpr int X_SIZE = X_UT + 512 * (U_CH / 16);
__device__ __align__(128) uint4 g_x[X_SIZE];
extern __shared__ uint8_t smem_raw[];
#define TS(i) do {} while (0)
#define TS1(i) do {} while (0)
#define GT(i) do {} while (0)
#define TSDUMP(base) do {} while (0)

__device__ __forceinline__ uint32_t smem_u32(const void* p) { return (uint32_t)__cvta_generic_to_shared(p); }
__device__ __forceinline__ void mbar_arrive(uint32_t b) {
  asm volatile("mbarrier.arrive.shared::cta.b64 _, [%0];" ::"r"(b) : "memory");
}
__device__ __forceinline__ void mbar_wait(uint32_t b) {
  uint32_t done = 0;
#pragma unroll 1
  for (int i = 0; i < SPIN_MAX && !done; i++) {
    asm volatile("{\n.reg .pred p;\nmbarrier.try_wait.parity.shared::cta.b64 p, [%1], 0, 4000;\nselp.u32 %0, 1, 0, p;\n}\n"
                 : "=r"(done) : "r"(b) : "memory");
  }
}
__device__ __forceinline__ void mbar_spin(uint32_t b) {
  uint32_t done = 0;
#pragma unroll 1
  for (int i = 0; i < (SPIN_MAX << 4) && !done; i++) {
    asm volatile("{\n.reg .pred p;\nmbarrier.try_wait.parity.shared::cta.b64 p, [%1], 0;\nselp.u32 %0, 1, 0, p;\n}\n"
                 : "=r"(done) : "r"(b) : "memory");
  }
}
__device__ __forceinline__ void mbar_init(uint32_t b, int n) {
  asm volatile("mbarrier.init.shared::cta.b64 [%0], %1;" ::"r"(b), "r"(n) : "memory");
}
__device__ __forceinline__ void mbar_expect(uint32_t b, int bytes) {
  asm volatile("mbarrier.arrive.expect_tx.shared::cta.b64 _, [%0], %1;" ::"r"(b), "r"(bytes) : "memory");
}
__device__ __forceinline__ void nb_sync(int id, int n) { asm volatile("bar.sync %0, %1;" ::"r"(id), "r"(n) : "memory"); }
__device__ __forceinline__ void nb_arrive(int id, int n) { asm volatile("bar.arrive %0, %1;" ::"r"(id), "r"(n) : "memory"); }
#define ELECT "{\n.reg .pred p;\nelect.sync _|p, 0xffffffff;\n@p "
__device__ __forceinline__ void e_expect(uint32_t b, int bytes) {
  asm volatile(ELECT "mbarrier.arrive.expect_tx.shared::cta.b64 _, [%0], %1;\n}\n" ::"r"(b), "r"(bytes) : "memory");
}
__device__ __forceinline__ void e_tma2d(uint32_t dst, const CUtensorMap* m, uint32_t bar, int c0, int c1) {
  asm volatile(ELECT "cp.async.bulk.tensor.2d.shared::cluster.global.mbarrier::complete_tx::bytes [%0], [%1, {%3,%4}], [%2];\n}\n"
               ::"r"(dst), "l"(m), "r"(bar), "r"(c0), "r"(c1) : "memory");
}
__device__ __forceinline__ void e_tma3d(uint32_t dst, const CUtensorMap* m, uint32_t bar, int c0, int c1, int c2) {
  asm volatile(ELECT "cp.async.bulk.tensor.3d.shared::cluster.global.mbarrier::complete_tx::bytes [%0], [%1, {%3,%4,%5}], [%2];\n}\n"
               ::"r"(dst), "l"(m), "r"(bar), "r"(c0), "r"(c1), "r"(c2) : "memory");
}
__device__ __forceinline__ void e_tma4d(uint32_t dst, const CUtensorMap* m, uint32_t bar, int c0, int c3) {
  asm volatile(ELECT "cp.async.bulk.tensor.4d.shared::cluster.global.mbarrier::complete_tx::bytes [%0], [%1, {%3,%5,%5,%4}], [%2];\n}\n"
               ::"r"(dst), "l"(m), "r"(bar), "r"(c0), "r"(c3), "r"(0) : "memory");
}
__device__ __forceinline__ void e_tma5d(uint32_t dst, const CUtensorMap* m, uint32_t bar, int c0, int c4) {
  asm volatile(ELECT "cp.async.bulk.tensor.5d.shared::cluster.global.mbarrier::complete_tx::bytes [%0], [%1, {%3,%5,%5,%5,%4}], [%2];\n}\n"
               ::"r"(dst), "l"(m), "r"(bar), "r"(c0), "r"(c4), "r"(0) : "memory");
}
__device__ __forceinline__ void e_bulk(uint32_t dst, const void* src, int bytes, uint32_t bar) {
  asm volatile(ELECT "cp.async.bulk.shared::cluster.global.mbarrier::complete_tx::bytes [%0], [%1], %2, [%3];\n}\n"
               ::"r"(dst), "l"(src), "r"(bytes), "r"(bar) : "memory");
}
__device__ __forceinline__ void e_prefetch(const void* p, int bytes) {
  asm volatile(ELECT "cp.async.bulk.prefetch.L2.global [%0], %1;\n}\n" ::"l"(p), "r"(bytes) : "memory");
}
__device__ __forceinline__ void e_store3d(const CUtensorMap* m, uint32_t src, int c1, int c2) {
  asm volatile(ELECT "cp.async.bulk.tensor.3d.global.shared::cta.bulk_group [%0, {%4,%2,%3}], [%1];\n"
               "@p cp.async.bulk.commit_group;\n@p cp.async.bulk.wait_group.read 0;\n}\n"
               ::"l"(m), "r"(src), "r"(c1), "r"(c2), "r"(0) : "memory");
}
__host__ __device__ constexpr uint64_t mkdesc(uint32_t addr, uint32_t lbo, uint32_t sbo, int swz) {
  return (uint64_t)((addr & 0x3FFFF) >> 4) | ((uint64_t)(lbo >> 4) << 16) | ((uint64_t)(sbo >> 4) << 32) |
         ((uint64_t)swz << 62);
}
#define WG_FENCE() asm volatile("wgmma.fence.sync.aligned;" ::: "memory")
#define WG_COMMIT() asm volatile("wgmma.commit_group.sync.aligned;" ::: "memory")
#define WG_WAIT(n) asm volatile("wgmma.wait_group.sync.aligned " #n ";" ::: "memory")

__device__ __forceinline__ void mma(float& d0, float& d1, float& d2, float& d3, uint32_t a0, uint32_t a1, uint32_t a2,
                                    uint32_t a3, uint32_t b0, uint32_t b1) {
  asm volatile("mma.sync.aligned.m16n8k16.row.col.f32.bf16.bf16.f32 {%0,%1,%2,%3},{%4,%5,%6,%7},{%8,%9},{%0,%1,%2,%3};"
               : "+f"(d0), "+f"(d1), "+f"(d2), "+f"(d3)
               : "r"(a0), "r"(a1), "r"(a2), "r"(a3), "r"(b0), "r"(b1));
}
__device__ __forceinline__ void mmac(float (&d)[4], uint32_t a0, uint32_t a1, uint32_t a2, uint32_t a3, uint32_t b0,
                                     uint32_t b1, const float (&c)[4]) {
  asm volatile("mma.sync.aligned.m16n8k16.row.col.f32.bf16.bf16.f32 {%0,%1,%2,%3},{%4,%5,%6,%7},{%8,%9},{%10,%11,%12,%13};"
               : "=f"(d[0]), "=f"(d[1]), "=f"(d[2]), "=f"(d[3])
               : "r"(a0), "r"(a1), "r"(a2), "r"(a3), "r"(b0), "r"(b1), "f"(c[0]), "f"(c[1]), "f"(c[2]), "f"(c[3]));
}
__device__ __forceinline__ void mma_p(int p, float (&d)[4], uint32_t a0, uint32_t a1, uint32_t a2, uint32_t a3, uint32_t b0, uint32_t b1) {
  asm volatile("{\n.reg .pred q;\nsetp.ne.b32 q, %10, 0;\n"
               "@q mma.sync.aligned.m16n8k16.row.col.f32.bf16.bf16.f32 {%0,%1,%2,%3},{%4,%5,%6,%7},{%8,%9},{%0,%1,%2,%3};\n}\n"
               : "+f"(d[0]), "+f"(d[1]), "+f"(d[2]), "+f"(d[3])
               : "r"(a0), "r"(a1), "r"(a2), "r"(a3), "r"(b0), "r"(b1), "r"(p));
}
__device__ __forceinline__ void mmac_p(int p, float (&d)[4], uint32_t a0, uint32_t a1, uint32_t a2, uint32_t a3, uint32_t b0,
                                       uint32_t b1, const float (&c)[4]) {
  asm volatile("{\n.reg .pred q;\nsetp.ne.b32 q, %14, 0;\n"
               "@q mma.sync.aligned.m16n8k16.row.col.f32.bf16.bf16.f32 {%0,%1,%2,%3},{%4,%5,%6,%7},{%8,%9},{%10,%11,%12,%13};\n}\n"
               : "+f"(d[0]), "+f"(d[1]), "+f"(d[2]), "+f"(d[3])
               : "r"(a0), "r"(a1), "r"(a2), "r"(a3), "r"(b0), "r"(b1), "f"(c[0]), "f"(c[1]), "f"(c[2]), "f"(c[3]), "r"(p));
}
__device__ __forceinline__ void mma_h(float (&d)[4], const uint32_t (&a)[4], uint32_t b0, uint32_t b1) {
  asm volatile("mma.sync.aligned.m16n8k16.row.col.f32.f16.f16.f32 {%0,%1,%2,%3},{%4,%5,%6,%7},{%8,%9},{%0,%1,%2,%3};"
               : "+f"(d[0]), "+f"(d[1]), "+f"(d[2]), "+f"(d[3]) : "r"(a[0]), "r"(a[1]), "r"(a[2]), "r"(a[3]), "r"(b0), "r"(b1));
}
__device__ __forceinline__ void mma0(float& d0, float& d1, float& d2, float& d3, uint32_t a0, uint32_t a1, uint32_t a2,
                                     uint32_t a3, uint32_t b0, uint32_t b1) {
  asm volatile("mma.sync.aligned.m16n8k16.row.col.f32.bf16.bf16.f32 {%0,%1,%2,%3},{%4,%5,%6,%7},{%8,%9},{%10,%10,%10,%10};"
               : "=f"(d0), "=f"(d1), "=f"(d2), "=f"(d3)
               : "r"(a0), "r"(a1), "r"(a2), "r"(a3), "r"(b0), "r"(b1), "f"(0.f));
}
__device__ __forceinline__ uint32_t pack_bf(float lo, float hi) {
  uint32_t r;
  asm("cvt.rn.bf16x2.f32 %0, %1, %2;" : "=r"(r) : "f"(hi), "f"(lo));
  return r;
}
__device__ __forceinline__ float bf_lo(uint32_t w) { return __uint_as_float(w << 16); }
__device__ __forceinline__ float bf_hi(uint32_t w) { return __uint_as_float(w & 0xffff0000u); }
__device__ __forceinline__ float bf_round(float x) { return __bfloat162float(__float2bfloat16_rn(x)); }
__device__ __forceinline__ uint32_t bmax2(uint32_t a, uint32_t b) {
  uint32_t r; asm("max.bf16x2 %0, %1, %2;" : "=r"(r) : "r"(a), "r"(b)); return r;
}
__device__ __forceinline__ uint32_t bmin2(uint32_t a, uint32_t b) {
  uint32_t r; asm("min.bf16x2 %0, %1, %2;" : "=r"(r) : "r"(a), "r"(b)); return r;
}
__device__ __forceinline__ float ex2(float x) { float r; asm("ex2.approx.ftz.f32 %0, %1;" : "=f"(r) : "f"(x)); return r; }
__device__ __forceinline__ float rcp(float x) { float r; asm("rcp.approx.ftz.f32 %0, %1;" : "=f"(r) : "f"(x)); return r; }
__device__ __forceinline__ void ldsm4(uint32_t (&r)[4], uint32_t a) {
  asm volatile("ldmatrix.sync.aligned.m8n8.x4.shared.b16 {%0,%1,%2,%3}, [%4];"
               : "=r"(r[0]), "=r"(r[1]), "=r"(r[2]), "=r"(r[3]) : "r"(a) : "memory");
}
__device__ __forceinline__ void ldsm4t(uint32_t (&r)[4], uint32_t a) {
  asm volatile("ldmatrix.sync.aligned.m8n8.x4.trans.shared.b16 {%0,%1,%2,%3}, [%4];"
               : "=r"(r[0]), "=r"(r[1]), "=r"(r[2]), "=r"(r[3]) : "r"(a) : "memory");
}
__device__ __forceinline__ void stsm4(uint32_t a, uint32_t r0, uint32_t r1, uint32_t r2, uint32_t r3) {
  asm volatile("stmatrix.sync.aligned.m8n8.x4.shared.b16 [%0], {%1,%2,%3,%4};"
               ::"r"(a), "r"(r0), "r"(r1), "r"(r2), "r"(r3) : "memory");
}
__device__ __forceinline__ uint32_t lds32(uint32_t a) {
  uint32_t r; asm volatile("ld.shared.u32 %0, [%1];" : "=r"(r) : "r"(a) : "memory"); return r;
}
__device__ __forceinline__ uint32_t lds16(uint32_t a) {
  uint32_t r; asm volatile("{\n.reg .u16 h;\nld.shared.u16 h, [%1];\ncvt.u32.u16 %0, h;\n}\n" : "=r"(r) : "r"(a) : "memory"); return r;
}
__device__ __forceinline__ uint2 lds64(uint32_t a) {
  uint2 r; asm volatile("ld.shared.v2.u32 {%0,%1}, [%2];" : "=r"(r.x), "=r"(r.y) : "r"(a) : "memory"); return r;
}
__device__ __forceinline__ uint4 lds128(uint32_t a) {
  uint4 r;
  asm volatile("ld.shared.v4.u32 {%0,%1,%2,%3}, [%4];" : "=r"(r.x), "=r"(r.y), "=r"(r.z), "=r"(r.w) : "r"(a) : "memory");
  return r;
}
__device__ __forceinline__ void sts32(uint32_t a, uint32_t v) { asm volatile("st.shared.u32 [%0], %1;" ::"r"(a), "r"(v) : "memory"); }
__device__ __forceinline__ void sts16(uint32_t a, uint32_t v) {
  asm volatile("{\n.reg .u16 h;\ncvt.u16.u32 h, %1;\nst.shared.u16 [%0], h;\n}\n" ::"r"(a), "r"(v) : "memory");
}
__device__ __forceinline__ void sts64(uint32_t a, uint32_t x, uint32_t y) {
  asm volatile("st.shared.v2.u32 [%0], {%1,%2};" ::"r"(a), "r"(x), "r"(y) : "memory");
}
__device__ __forceinline__ void sts128(uint32_t a, uint32_t x, uint32_t y, uint32_t z, uint32_t w) {
  asm volatile("st.shared.v4.u32 [%0], {%1,%2,%3,%4};" ::"r"(a), "r"(x), "r"(y), "r"(z), "r"(w) : "memory");
}
__device__ __forceinline__ uint4 ld_x(const uint4* p) {
  uint4 r;
  asm volatile("{\n.reg .b128 t;\nld.relaxed.gpu.global.b128 t, [%4];\nmov.b128 {%0,%1,%2,%3}, t;\n}\n"
               : "=r"(r.x), "=r"(r.y), "=r"(r.z), "=r"(r.w) : "l"(p) : "memory");
  return r;
}
__device__ __forceinline__ uint32_t ld_x32(const uint32_t* p) {
  uint32_t r; asm volatile("ld.relaxed.gpu.global.u32 %0, [%1];" : "=r"(r) : "l"(p) : "memory"); return r;
}
__device__ __forceinline__ void st_x(uint4* p, uint32_t x, uint32_t y, uint32_t z, uint32_t w) {
  asm volatile("{\n.reg .b128 t;\nmov.b128 t, {%1,%2,%3,%4};\nst.relaxed.gpu.global.b128 [%0], t;\n}\n"
               ::"l"(p), "r"(x), "r"(y), "r"(z), "r"(w) : "memory");
}
__device__ __forceinline__ void st_x_p(int p, uint4* a, uint32_t x, uint32_t y, uint32_t z, uint32_t w) {
  asm volatile("{\n.reg .b128 t;\n.reg .pred q;\nsetp.ne.b32 q, %5, 0;\nmov.b128 t, {%1,%2,%3,%4};\n@q st.relaxed.gpu.global.b128 [%0], t;\n}\n"
               ::"l"(a), "r"(x), "r"(y), "r"(z), "r"(w), "r"(p) : "memory");
}
__device__ __forceinline__ void sts64_p(int p, uint32_t a, uint32_t x, uint32_t y) {
  asm volatile("{\n.reg .pred q;\nsetp.ne.b32 q, %3, 0;\n@q st.shared.v2.u32 [%0], {%1,%2};\n}\n" ::"r"(a), "r"(x), "r"(y), "r"(p) : "memory");
}
__device__ __forceinline__ void st_x32(uint32_t* p, uint32_t x) {
  asm volatile("st.relaxed.gpu.global.u32 [%0], %1;" ::"l"(p), "r"(x) : "memory");
}
__device__ __forceinline__ uint32_t nz(uint32_t w) { return max(w, 1u); }
__device__ __forceinline__ uint32_t fu(float x) { return __float_as_uint(x); }
__device__ __forceinline__ float uf(uint32_t x) { return __uint_as_float(x); }

__device__ __forceinline__ void wgmma_ss_n96(float (&d)[48], uint64_t da, uint64_t db, int sc) {
  asm volatile("{\n.reg .pred p;\nsetp.ne.b32 p, %50, 0;\n"
      "wgmma.mma_async.sync.aligned.m64n96k16.f32.bf16.bf16 "
      "{%0,%1,%2,%3,%4,%5,%6,%7,%8,%9,%10,%11,%12,%13,%14,%15,%16,%17,%18,%19,%20,%21,%22,%23,%24,%25,%26,%27,%28,%29,%30,%31,%32,%33,%34,%35,%36,%37,%38,%39,%40,%41,%42,%43,%44,%45,%46,%47}, "
      "%48, %49, p, 1, 1, 0, 1;\n}\n"
      : "+f"(d[0]), "+f"(d[1]), "+f"(d[2]), "+f"(d[3]), "+f"(d[4]), "+f"(d[5]), "+f"(d[6]), "+f"(d[7]),
        "+f"(d[8]), "+f"(d[9]), "+f"(d[10]), "+f"(d[11]), "+f"(d[12]), "+f"(d[13]), "+f"(d[14]), "+f"(d[15]),
        "+f"(d[16]), "+f"(d[17]), "+f"(d[18]), "+f"(d[19]), "+f"(d[20]), "+f"(d[21]), "+f"(d[22]), "+f"(d[23]),
        "+f"(d[24]), "+f"(d[25]), "+f"(d[26]), "+f"(d[27]), "+f"(d[28]), "+f"(d[29]), "+f"(d[30]), "+f"(d[31]),
        "+f"(d[32]), "+f"(d[33]), "+f"(d[34]), "+f"(d[35]), "+f"(d[36]), "+f"(d[37]), "+f"(d[38]), "+f"(d[39]),
        "+f"(d[40]), "+f"(d[41]), "+f"(d[42]), "+f"(d[43]), "+f"(d[44]), "+f"(d[45]), "+f"(d[46]), "+f"(d[47])
      : "l"(da), "l"(db), "r"(sc));
}

__device__ __forceinline__ void wgmma_ss_n128(float (&d)[64], uint64_t da, uint64_t db, int sc) {
  asm volatile("{\n.reg .pred p;\nsetp.ne.b32 p, %66, 0;\n"
      "wgmma.mma_async.sync.aligned.m64n128k16.f32.bf16.bf16 "
      "{%0,%1,%2,%3,%4,%5,%6,%7,%8,%9,%10,%11,%12,%13,%14,%15,%16,%17,%18,%19,%20,%21,%22,%23,%24,%25,%26,%27,%28,%29,%30,%31,%32,%33,%34,%35,%36,%37,%38,%39,%40,%41,%42,%43,%44,%45,%46,%47,%48,%49,%50,%51,%52,%53,%54,%55,%56,%57,%58,%59,%60,%61,%62,%63}, "
      "%64, %65, p, 1, 1, 0, 1;\n}\n"
      : "+f"(d[0]), "+f"(d[1]), "+f"(d[2]), "+f"(d[3]), "+f"(d[4]), "+f"(d[5]), "+f"(d[6]), "+f"(d[7]),
        "+f"(d[8]), "+f"(d[9]), "+f"(d[10]), "+f"(d[11]), "+f"(d[12]), "+f"(d[13]), "+f"(d[14]), "+f"(d[15]),
        "+f"(d[16]), "+f"(d[17]), "+f"(d[18]), "+f"(d[19]), "+f"(d[20]), "+f"(d[21]), "+f"(d[22]), "+f"(d[23]),
        "+f"(d[24]), "+f"(d[25]), "+f"(d[26]), "+f"(d[27]), "+f"(d[28]), "+f"(d[29]), "+f"(d[30]), "+f"(d[31]),
        "+f"(d[32]), "+f"(d[33]), "+f"(d[34]), "+f"(d[35]), "+f"(d[36]), "+f"(d[37]), "+f"(d[38]), "+f"(d[39]),
        "+f"(d[40]), "+f"(d[41]), "+f"(d[42]), "+f"(d[43]), "+f"(d[44]), "+f"(d[45]), "+f"(d[46]), "+f"(d[47]),
        "+f"(d[48]), "+f"(d[49]), "+f"(d[50]), "+f"(d[51]), "+f"(d[52]), "+f"(d[53]), "+f"(d[54]), "+f"(d[55]),
        "+f"(d[56]), "+f"(d[57]), "+f"(d[58]), "+f"(d[59]), "+f"(d[60]), "+f"(d[61]), "+f"(d[62]), "+f"(d[63])
      : "l"(da), "l"(db), "r"(sc));
}

__device__ __forceinline__ void wgmma_ss_n40(float (&d)[20], uint64_t da, uint64_t db, int sc) {
  asm volatile("{\n.reg .pred p;\nsetp.ne.b32 p, %22, 0;\n"
      "wgmma.mma_async.sync.aligned.m64n40k16.f32.bf16.bf16 "
      "{%0,%1,%2,%3,%4,%5,%6,%7,%8,%9,%10,%11,%12,%13,%14,%15,%16,%17,%18,%19}, "
      "%20, %21, p, 1, 1, 1, 1;\n}\n"
      : "+f"(d[0]), "+f"(d[1]), "+f"(d[2]), "+f"(d[3]), "+f"(d[4]), "+f"(d[5]), "+f"(d[6]), "+f"(d[7]),
        "+f"(d[8]), "+f"(d[9]), "+f"(d[10]), "+f"(d[11]), "+f"(d[12]), "+f"(d[13]), "+f"(d[14]), "+f"(d[15]),
        "+f"(d[16]), "+f"(d[17]), "+f"(d[18]), "+f"(d[19])
      : "l"(da), "l"(db), "r"(sc));
}

__device__ __forceinline__ void wgmma_rs_n8(float (&d)[4], const uint4& a, uint64_t db, int sc) {
  asm volatile("{\n.reg .pred p;\nsetp.ne.b32 p, %9, 0;\n"
      "wgmma.mma_async.sync.aligned.m64n8k16.f32.bf16.bf16 "
      "{%0,%1,%2,%3}, "
      "{%4,%5,%6,%7}, %8, p, 1, 1, 1;\n}\n"
      : "+f"(d[0]), "+f"(d[1]), "+f"(d[2]), "+f"(d[3])
      : "r"(a.x), "r"(a.y), "r"(a.z), "r"(a.w), "l"(db), "r"(sc));
}

__device__ __forceinline__ void wgmma_rs_n16(float (&d)[8], const uint4& a, uint64_t db, int sc) {
  asm volatile("{\n.reg .pred p;\nsetp.ne.b32 p, %13, 0;\n"
      "wgmma.mma_async.sync.aligned.m64n16k16.f32.bf16.bf16 "
      "{%0,%1,%2,%3,%4,%5,%6,%7}, "
      "{%8,%9,%10,%11}, %12, p, 1, 1, 1;\n}\n"
      : "+f"(d[0]), "+f"(d[1]), "+f"(d[2]), "+f"(d[3]), "+f"(d[4]), "+f"(d[5]), "+f"(d[6]), "+f"(d[7])
      : "r"(a.x), "r"(a.y), "r"(a.z), "r"(a.w), "l"(db), "r"(sc));
}

__device__ __forceinline__ void wgmma_rs_n24(float (&d)[12], const uint4& a, uint64_t db, int sc) {
  asm volatile("{\n.reg .pred p;\nsetp.ne.b32 p, %17, 0;\n"
      "wgmma.mma_async.sync.aligned.m64n24k16.f32.bf16.bf16 "
      "{%0,%1,%2,%3,%4,%5,%6,%7,%8,%9,%10,%11}, "
      "{%12,%13,%14,%15}, %16, p, 1, 1, 1;\n}\n"
      : "+f"(d[0]), "+f"(d[1]), "+f"(d[2]), "+f"(d[3]), "+f"(d[4]), "+f"(d[5]), "+f"(d[6]), "+f"(d[7]),
        "+f"(d[8]), "+f"(d[9]), "+f"(d[10]), "+f"(d[11])
      : "r"(a.x), "r"(a.y), "r"(a.z), "r"(a.w), "l"(db), "r"(sc));
}

struct Params {
  const __nv_bfloat16 *logA, *Aim, *Cre, *Cim, *logdt, *Dskip, *x, *wphi, *wo;
  __nv_bfloat16* out;
  uint4* xs;
  long long* ts;
};

__device__ __forceinline__ uint4 tr_row(const uint4 (&v)[8], int i) {
  uint32_t o[4];
#pragma unroll
  for (int m = 0; m < 4; m++) {
    const uint4 &ra = v[2 * m], &rb = v[2 * m + 1];
    const int k = i >> 1;
    const uint32_t xa = k == 0 ? ra.x : k == 1 ? ra.y : k == 2 ? ra.z : ra.w;
    const uint32_t xb = k == 0 ? rb.x : k == 1 ? rb.y : k == 2 ? rb.z : rb.w;
    o[m] = __byte_perm(xa, xb, (i & 1) ? 0x7632 : 0x5410);
  }
  return make_uint4(o[0], o[1], o[2], o[3]);
}

struct cpx { float r, i; };
__device__ __forceinline__ cpx csq(cpx a) { return {a.r * a.r - a.i * a.i, 2.f * (a.r * a.i)}; }
__device__ __forceinline__ cpx polar(float e, float t) {
  const float m = ex2(e);
  return {m * __cosf(t), m * __sinf(t)};
}

struct KgenRaw { unsigned short la, ai, cr, ci, ldt; };
__device__ __forceinline__ KgenRaw kgen_load(const Params& P, int d, int unit, int lane) {
  const int o = d * 128 + unit * 32 + lane;
  return {__ldg((const unsigned short*)P.logA + o), __ldg((const unsigned short*)P.Aim + o), __ldg((const unsigned short*)P.Cre + o),
          __ldg((const unsigned short*)P.Cim + o), __ldg((const unsigned short*)P.logdt + d)};
}
struct hmul { __half2 a, b; };
__device__ __forceinline__ hmul mk_mul(cpx w) {
  uint32_t b;
  asm("{\n.reg .f32 n;\nneg.ftz.f32 n, %1;\ncvt.rn.f16x2.f32 %0, %2, n;\n}\n" : "=r"(b) : "f"(w.i), "f"(w.r));
  return {__floats2half2_rn(w.r, w.i), *(const __half2*)&b};
}
__device__ __forceinline__ __half2 hcm(__half2 z, const hmul& w) { return __hfma2(__high2half2(z), w.b, __hmul2(__low2half2(z), w.a)); }
__device__ __forceinline__ uint32_t hu(__half2 v) { return *(const uint32_t*)&v; }

struct KgenAddr { uint32_t sa, sb, lb, lc, la; };
__device__ __forceinline__ KgenAddr kgen_addr(int lane, uint32_t buf) {
  KgenAddr a;
  a.sa = buf + (lane & 7) * 128 + ((((lane >> 3) ^ lane) & 7) << 4);
  a.lb = buf + (lane >> 3) * 128 + (((lane ^ (lane >> 3)) & 7) << 4);
  a.la = buf + ((lane >> 3) & 1) * 1024 + (lane >> 4) * 128 + (((lane ^ (lane >> 4)) & 7) << 4);
  a.sb = a.sa ^ 64; a.lc = a.lb ^ 64;
  asm volatile("" : "+r"(a.sa), "+r"(a.sb), "+r"(a.lb), "+r"(a.lc), "+r"(a.la));
  return a;
}
__device__ __forceinline__ void kgen_unit(const KgenRaw& r, const KgenAddr& ad, uint32_t zero, float (&k)[5][4], float& k2048, float& sc) {
  const float dt = bf_round(expf(bf_lo(r.ldt)));
  const float a2 = bf_round(ex2(bf_lo(r.la) * 1.4426950408889634f)) * (dt * -1.4426950408889634f);
  const float f = bf_lo(r.ai) * dt;
  const float r128 = f * 20.371832715762604f;
  const uint32_t ex = min(max(__reduce_max_sync(0xffffffffu, max(r.cr & 0x7fffu, r.ci & 0x7fffu)) >> 7, 1u), 253u);
  const float cs = uf((254u - ex) << 23);
  sc = 2.f * dt * uf(ex << 23);
  const cpx C = {bf_lo(r.cr) * cs, -bf_lo(r.ci) * cs};
  auto put = [&](const __half2 (&v)[8], uint32_t off) {
    stsm4(ad.sa + off, hu(v[0]), hu(v[1]), hu(v[2]), hu(v[3]));
    stsm4(ad.sb + off, hu(v[4]), hu(v[5]), hu(v[6]), hu(v[7]));
  };
  uint32_t A[4][4], B[5][2][4];
  auto get = [&](int j, uint32_t off) {
    __syncwarp();
    ldsm4(B[j][0], ad.lb + off);
    ldsm4(B[j][1], ad.lc + 512 + off);
  };
  auto tile = [&](int j) {
    k[j][0] = k[j][1] = k[j][2] = k[j][3] = 0.f;
#pragma unroll
    for (int s = 0; s < 4; s++) mma_h(k[j], A[s], B[j][s >> 1][2 * (s & 1)], B[j][s >> 1][2 * (s & 1) + 1]);
  };
  auto after = [&](cpx v, uint32_t dep) { return cpx{uf(fu(v.r) ^ (dep & zero)), v.i}; };
  const cpx w1 = polar(a2, f), w128 = polar(a2 * 128.f, (r128 - rintf(r128)) * 6.283185307179586f);
  const cpx w2 = csq(w1), w4 = csq(w2);
  __half2 t0[8], t1[8], t2[8], t3[8], t4[8];
  const hmul m2 = mk_mul(w2), m4 = mk_mul(w4), m128 = mk_mul(w128);
  t0[0] = __floats2half2_rn(1.f, 0.f); t0[1] = __floats2half2_rn(w1.r, w1.i); t0[2] = m2.a; t0[4] = m4.a;
  t0[3] = hcm(t0[1], m2); t0[5] = hcm(t0[1], m4); t0[6] = hcm(t0[2], m4); t0[7] = hcm(t0[3], m4);
  put(t0, 0); get(0, 0);
  t1[0] = m128.a;
#pragma unroll
  for (int i = 1; i < 8; i++) t1[i] = hcm(t0[i], m128);
  put(t1, 1024); get(1, 1024);
  {
    cpx w8 = csq(after(w4, B[0][0][0]));
    w8.i = -w8.i;
    const cpx w16 = csq(w8), w32 = csq(w16), w64 = csq(w32);
    const hmul m8 = mk_mul(w8), m16 = mk_mul(w16), m32 = mk_mul(w32), m64 = mk_mul(w64);
    __half2 a[8];
    a[0] = __floats2half2_rn(C.r, C.i); a[1] = hcm(a[0], m8);
    a[2] = hcm(a[0], m16); a[3] = hcm(a[1], m16);
#pragma unroll
    for (int i = 0; i < 4; i++) a[4 + i] = hcm(a[i], m32);
    put(a, 0);
#pragma unroll
    for (int i = 0; i < 8; i++) a[i] = hcm(a[i], m64);
    put(a, 1024);
    __syncwarp();
#pragma unroll
    for (int s = 0; s < 4; s++) ldsm4(A[s], (ad.la ^ (s << 5)) + s * 256);
  }
  const cpx w256 = csq(after(w128, B[1][0][0]));
  const hmul m256 = mk_mul(w256);
  t2[0] = m256.a;
#pragma unroll
  for (int i = 1; i < 8; i++) t2[i] = hcm((i & 1) ? t1[i & 6] : t0[i & 6], m256);
  put(t2, 0); get(2, 0);
  tile(0); tile(1);
  const cpx w512 = csq(after(w256, A[0][0]));
  const hmul m512 = mk_mul(w512);
  t3[0] = m512.a;
#pragma unroll
  for (int i = 1; i < 8; i++) t3[i] = hcm((i & 2) ? t2[i & 5] : ((i & 1) ? t1[i & 4] : t0[i & 4]), m512);
  put(t3, 1024); get(3, 1024);
  tile(2);
  const cpx w1024 = csq(after(w512, B[2][0][0])), we = csq(w1024);
  const hmul m1024 = mk_mul(w1024);
  t4[0] = m1024.a;
#pragma unroll
  for (int i = 1; i < 8; i++) t4[i] = hcm((i & 4) ? t3[i & 3] : ((i & 2) ? t2[i & 1] : t1[0]), m1024);
  put(t4, 0); get(4, 0);
  tile(3); tile(4);
  k2048 = (C.r * we.r + C.i * we.i) * sc;
}

__device__ __forceinline__ void build_tables(uint32_t tb, int lane, float (&k)[5][4], float k2048) {
  const int g = lane >> 2, c = lane & 3;
  const uint32_t kc = tb + T_KC + 16;
  {
    const uint32_t a0 = kc + 16 * g + 4 * c, a2 = kc + 2 * (256 + 4 * g + c);
    const uint32_t a3 = kc + 2 * (384 + 2 * g + 64 * (c & 1) + (c >> 1)), a4 = kc + 2 * (512 + g + 32 * c);
#pragma unroll
    for (int r = 0; r < 2; r++) {
      sts32(a0 + 128 * r, pack_bf(k[0][2 * r], k[0][2 * r + 1]));
      sts32(a0 + 128 * r + 256, pack_bf(k[1][2 * r], k[1][2 * r + 1]));
      const uint32_t w2 = pack_bf(k[2][2 * r], k[2][2 * r + 1]);
      const uint32_t w3 = pack_bf(k[3][2 * r], k[3][2 * r + 1]);
      const uint32_t w4 = pack_bf(k[4][2 * r], k[4][2 * r + 1]);
      sts16(a2 + 64 * r, w2); sts16(a2 + 64 * r + 128, w2 >> 16);
      sts16(a3 + 32 * r, w3); sts16(a3 + 32 * r + 64, w3 >> 16);
      sts16(a4 + 16 * r, w4); sts16(a4 + 16 * r + 32, w4 >> 16);
    }
  }
  if (lane == 0) { sts16(kc + 2 * 640, pack_bf(k2048, 0.f)); sts16(kc - 2, 0); }
  __syncwarp();
  const uint32_t td = tb + T_D + 32;
  {
    const uint4 v = lds128(kc + 16 * lane);
    const uint32_t pv = lds16(kc + 16 * lane - 2);
    sts128(td + 32 * lane, __byte_perm(v.x, pv, 0x5410), __byte_perm(v.x, v.x, 0x1032), __byte_perm(v.y, v.x, 0x7610),
           __byte_perm(v.y, v.y, 0x1032));
    sts128(td + 32 * lane + 16, __byte_perm(v.z, v.y, 0x7610), __byte_perm(v.z, v.z, 0x1032),
           __byte_perm(v.w, v.z, 0x7610), __byte_perm(v.w, v.w, 0x1032));
  }
  {
    const uint2 v = lds64(kc + 512 + 8 * lane);
    const uint32_t k4 = lds16(kc + 512 + 8 * lane + 8);
    const uint32_t pv = lds16(kc + (lane == 0 ? 510 : 512 + 8 * lane));
    const uint32_t k22 = __byte_perm(v.y, v.y, 0x1010);
    sts128(td + 1024 + 32 * lane, __byte_perm(v.x, pv, 0x5410), __byte_perm(v.x, v.x, 0x1010),
           __byte_perm(v.x, v.x, 0x1032), __byte_perm(v.y, v.x, 0x7610));
    sts128(td + 1024 + 32 * lane + 16, k22, k22, __byte_perm(v.y, v.y, 0x1032), __byte_perm(k4, v.y, 0x7610));
  }
  {
    const uint32_t kk = lds16(kc + 2 * 384);
    const uint32_t w = lane < 3 ? (kk | (kk << 16)) : (lane == 3 ? (kk << 16) : 0u);
    if (lane < 24) sts32(td + 4 * (lane < 16 ? 512 + lane : lane - 24), w);
    const uint32_t lo_ = lds16(kc + 2 * 511), le_ = lds16(kc + 2 * 512);
    const uint32_t ja = tb + T_5 + (lane < 16 ? 4 * lane : 256 + 4 * lane);
    sts32(ja, lane == 16 ? (le_ << 16) : 0u);
    sts32(ja + 384, lane == 16 ? (lo_ << 16) : 0u);
    sts32(tb + (lane < 16 ? T_7 : T_9 - 64) + 4 * lane, 0u);
  }
#pragma unroll
  for (int s = 0; s < 2; s++) {
    const uint32_t b = kc + 2 * (s ? 512 : 384) + 8 * lane;
    const uint2 v = lds64(b);
    uint32_t em = lds16(b - 2), e0 = v.x;
    const uint32_t e4 = lds16(b + 8);
    if (lane == 0) { em = 0; e0 = 0; }
    sts64(tb + (s ? T_7 : T_3) + 64 + 8 * lane, __byte_perm(v.x, em, 0x5432), __byte_perm(v.y, v.x, 0x7632));
    sts64(tb + (s ? T_9 : T_5) + 64 + 8 * lane, __byte_perm(v.y, e0, 0x5410), __byte_perm(e4, v.y, 0x5410));
  }
  __syncwarp();
}

__device__ __forceinline__ uint32_t box2w(int lo, int n, int o) {
  return ((unsigned)(o - lo) < (unsigned)n ? 0x3F80u : 0u) | ((unsigned)(o + 1 - lo) < (unsigned)n ? 0x3F800000u : 0u);
}

#define SPLIT() asm volatile("{\n.reg .pred p;\nsetp.ne.u32 p, %0, 0;\n@p exit;\n}\n" ::"r"(blockIdx.y) : "memory")

__device__ __forceinline__ void conv_channel(uint32_t ub, uint32_t tb, int lane, uint4* ydst) {
  const int g = lane >> 2, c = lane & 3, x = g - 2 * c;
  const int mi = lane >> 3;
  const uint32_t qa = ub + U_PAD + 16 * (lane & 7) + ((mi == 0 || mi == 3) ? U_ODD : 0) - (mi == 0 ? 16 : 0);
  const uint32_t hb = ub + U_PAD + (mi & 1) * U_ODD + 16 * ((lane >> 4) + (lane & 7)) - 16;
  const uint32_t kv = lds16(tb + T_KC + 16 + 2 * 512);
  const int oh = c < 2 ? 8 + 2 * c : 2 * c - 8, og = c < 3 ? 2 * c : -10;
  uint32_t bx[4] = {box2w(g - 4, 9, 2 * c), box2w(g - 3, 7, 2 * c), box2w(g - 4, 9, oh), box2w(g - 3, 7, oh)};
  uint32_t by[4] = {box2w(g - 10, 5, 2 * c - 8), box2w(g - 5, 3, 2 * c - 8), box2w(g - 10, 5, og), box2w(g - 5, 3, og)};
  uint32_t lb0 = ((unsigned)(x + 5) < 2u ? kv : 0u) | ((unsigned)(x + 4) < 2u ? kv << 16 : 0u);
  uint32_t lb1 = ((unsigned)(x - 3) < 2u ? kv : 0u) | ((unsigned)(x - 4) < 2u ? kv << 16 : 0u);
  const int q0 = g - 1, q1 = c < 3 ? g : g - 2;
  uint32_t y0a = ub + U_PAD + (q0 & 1) * U_ODD + 16 * (q0 >> 1) + 4 * c;
  uint32_t y1a = ub + U_PAD + (q1 & 1) * U_ODD + 16 * (q1 >> 1) + 4 * c;
  uint32_t f3[3][4][4];
  {
    const uint32_t fa = tb + T_7 + 4 * (16 + x);
#pragma unroll
    for (int tt = 0; tt < 3; tt++)
#pragma unroll
      for (int D = 0; D < 4; D++) {
        const uint32_t a = fa + (tt == 0 ? 316 : (tt == 1 ? 320 : 0)) + 64 * D;
        f3[tt][D][0] = lds32(a); f3[tt][D][1] = lds32(a + 32); f3[tt][D][2] = lds32(a - 32); f3[tt][D][3] = lds32(a);
      }
  }
#pragma unroll
  for (int i = 0; i < 4; i++) asm volatile("" : "+r"(bx[i]), "+r"(by[i]));
  asm volatile("" : "+r"(lb0), "+r"(lb1), "+r"(y0a), "+r"(y1a));
  mbar_wait(BAR(MB_UFULL));
  mbar_wait(BAR(MB_EMPTY + 15));
  TS(36);
  float acc[16][4];
  {
    uint32_t z09[8], z07[8], zm9[8], zm7[8];
#pragma unroll
    for (int i = 0; i < 8; i++) {
      uint32_t h[4];
      ldsm4(h, hb + 128 * i);
      float y0, y1, y2, y3, w0, w1, w2, w3;
      mma0(y0, y1, y2, y3, bx[0], bx[1], bx[2], bx[3], h[2], c < 2 ? h[3] : h[1]);
      mma0(w0, w1, w2, w3, bx[0], bx[1], bx[2], bx[3], h[1], c < 2 ? h[2] : h[0]);
      z09[i] = pack_bf(y0, y1); z07[i] = pack_bf(y2, y3);
      zm9[i] = pack_bf(w0, w1); zm7[i] = pack_bf(w2, w3);
    }
    float a[4][2][4];
#pragma unroll
    for (int kap = 0; kap < 4; kap++)
#pragma unroll
      for (int sg = 0; sg < 2; sg++)
#pragma unroll
        for (int bk = 3; bk >= kap; bk--) {
          const uint32_t(&q0_)[4] = f3[sg ? 2 : 0][bk - kap];
          const uint32_t(&q1_)[4] = f3[sg ? 2 : 1][bk - kap];
          float(&a0)[4] = a[bk][0];
          float(&a1)[4] = a[bk][1];
          if (sg == 0 && kap == 0) {
            mma0(a0[0], a0[1], a0[2], a0[3], q0_[0], q0_[1], q0_[2], q0_[3], z09[0], z09[1]);
            mma0(a1[0], a1[1], a1[2], a1[3], q1_[0], q1_[1], q1_[2], q1_[3], zm9[0], zm9[1]);
          } else {
            mma(a0[0], a0[1], a0[2], a0[3], q0_[0], q0_[1], q0_[2], q0_[3], sg ? zm7[2 * kap] : z09[2 * kap], sg ? zm7[2 * kap + 1] : z09[2 * kap + 1]);
            mma(a1[0], a1[1], a1[2], a1[3], q1_[0], q1_[1], q1_[2], q1_[3], sg ? z07[2 * kap] : zm9[2 * kap], sg ? z07[2 * kap + 1] : zm9[2 * kap + 1]);
          }
        }
    SPLIT();
#pragma unroll
    for (int i = 0; i < 8; i++) {
      uint32_t h[4];
      ldsm4(h, qa + 128 * i);
      const float ci[4] = {a[i >> 1][0][2 * (i & 1)], a[i >> 1][0][2 * (i & 1) + 1], a[i >> 1][1][2 * (i & 1)], a[i >> 1][1][2 * (i & 1) + 1]};
      mmac(acc[8 + i], h[0], h[1], h[2], h[3], lb0, lb1, ci);
    }
  }
  TS(44);
  {
    uint2 a5[10], a3[10];
    const uint32_t aa = tb + T_5 + 4 * (8 + 2 * g - 2 * c);
#pragma unroll
    for (int m = 0; m < 10; m++) { a5[m] = lds64(aa + 32 * m); a3[m] = lds64(aa + 384 + 32 * m); }
    uint32_t x5[12][2], x3[12][2];
    auto ygen = [&](int kap) {
#pragma unroll
      for (int hh = 0; hh < 2; hh++) {
        float y0, y1, y2, y3;
        mma0(y0, y1, y2, y3, by[0], by[1], by[2], by[3], lds32(y0a + 128 * kap + 64 * hh), lds32(y1a + 128 * kap + 64 * hh));
        x5[kap][hh] = pack_bf(y0, y1);
        x3[kap][hh] = pack_bf(y2, y3);
      }
    };
    ygen(11); ygen(10); ygen(9); ygen(8);
#pragma unroll
    for (int kap = 11; kap >= 0; kap--) {
      if (kap >= 4) ygen(kap - 4);
#pragma unroll
      for (int sg = 0; sg < 2; sg++)
#pragma unroll
        for (int i = 4; i >= 0; i--) {
          const int be = kap + 4 + i;
          if (be <= 15) {
            const uint2 &hi = sg ? a3[2 * i + 1] : a5[2 * i + 1], &lo = sg ? a3[2 * i] : a5[2 * i];
            const uint32_t b0 = sg ? x3[kap][0] : x5[kap][0], b1 = sg ? x3[kap][1] : x5[kap][1];
            if (be < 8 && i == 0 && sg == 0) mma0(acc[be][0], acc[be][1], acc[be][2], acc[be][3], hi.x, hi.y, lo.x, lo.y, b0, b1);
            else mma(acc[be][0], acc[be][1], acc[be][2], acc[be][3], hi.x, hi.y, lo.x, lo.y, b0, b1);
          }
        }
    }
  }
  TS(45);
  {
    const uint32_t st = tb + T_ST + lane * 8;
#pragma unroll
    for (int be = 4; be < 12; be++) sts64(st + 256 * be, pack_bf(acc[be][0], acc[be][1]), pack_bf(acc[be][2], acc[be][3]));
    SPLIT();
    uint32_t F[66], qd[8][4];
    const uint32_t fa = tb + T_D + 32 + 4 * x;
#pragma unroll
    for (int i = 0; i < 32; i++) {
      const int s = 120 - (i >> 2) - 8 * (i & 3);
      uint32_t(&q)[4] = qd[i & 7];
      ldsm4(q, qa + 16 * s);
      const int m = 16 * (i & 3) + 2 * (i >> 2);
      F[m] = lds32(fa + 32 * m); F[m + 1] = lds32(fa + 32 * m + 32);
#pragma unroll
      for (int be = 15; be >= 12; be--) {
        const int de = 8 * be - s;
        if (de >= 0) mma(acc[be][0], acc[be][1], acc[be][2], acc[be][3], q[0], q[1], q[2], q[3], F[2 * de + 1], F[2 * de]);
      }
    }
    F[64] = lds32(fa + 32 * 64); F[65] = lds32(fa + 32 * 65);
    uint32_t qp = qa + 128 * 11, sta = st + 256 * 10;
    uint4* yd = ydst + 7 * 32;
#pragma unroll
    for (int i = 0; i < 6; i++) ldsm4(qd[i], qp - 16 * i);
    uint2 sv = lds64(sta + 256);
    float ci[4] = {bf_lo(sv.x), bf_hi(sv.x), bf_lo(sv.y), bf_hi(sv.y)};
    float T[5][4];
#pragma unroll
    for (int i = 0; i < 16; i++) T[i >> 2][i & 3] = acc[12 + (i >> 2)][i & 3];
    nb_sync(NB_YZ, 160);
    TS(46);
#pragma unroll 1
    for (int bp = 5; bp >= 0; bp--) {
      uint32_t held[2];
#pragma unroll
      for (int o = 1; o >= 0; o--) {
#pragma unroll
        for (int k = 4; k >= 1; k--) mmac(T[k], qd[0][0], qd[0][1], qd[0][2], qd[0][3], F[16 * k + 1], F[16 * k], T[k - 1]);
        mmac(T[0], qd[0][0], qd[0][1], qd[0][2], qd[0][3], F[1], F[0], ci);
        ldsm4(qd[6], qp - 16 * 6);
        ldsm4(qd[7], qp - 16 * 7);
        sv = lds64(sta);
#pragma unroll
        for (int i = 1; i < 8; i++) {
#pragma unroll
          for (int k = 3; k >= 0; k--)
            mma(T[k][0], T[k][1], T[k][2], T[k][3], qd[i][0], qd[i][1], qd[i][2], qd[i][3], F[16 * k + 2 * i + 1], F[16 * k + 2 * i]);
          if (i < 7) ldsm4(qd[i - 1], qp - 128 - 16 * (i - 1));
          if (i == 2) {
            const uint32_t w0 = pack_bf(T[4][0], T[4][1]), w1 = pack_bf(T[4][2], T[4][3]);
            if (o) { held[0] = w0; held[1] = w1; }
            else st_x(yd, nz(w0), w1, held[0], held[1]);
          }
          if (i == 4) {
            if (2 * bp + o <= 4) sv = make_uint2(0, 0);
            ci[0] = bf_lo(sv.x); ci[1] = bf_hi(sv.x); ci[2] = bf_lo(sv.y); ci[3] = bf_hi(sv.y);
          }
        }
        qp -= 128; sta -= 256;
      }
      yd -= 32;
    }
#pragma unroll
    for (int B = 1; B >= 0; B--)
      st_x(ydst + B * 32, nz(pack_bf(T[2 * B][0], T[2 * B][1])), pack_bf(T[2 * B][2], T[2 * B][3]),
           pack_bf(T[2 * B + 1][0], T[2 * B + 1][1]), pack_bf(T[2 * B + 1][2], T[2 * B + 1][3]));
  }
}

__device__ __forceinline__ void dual_exp(const uint32_t* w, uint32_t* e) {
  const float L = 1.44268798828125f;
  uint32_t mx = bmax2(bmax2(w[0], w[1]), bmax2(w[2], w[3]));
  uint32_t mn = bmin2(bmin2(w[0], w[1]), bmin2(w[2], w[3]));
  mx = bmax2(mx, __shfl_xor_sync(0xffffffffu, mx, 1));
  mn = bmin2(mn, __shfl_xor_sync(0xffffffffu, mn, 1));
  mx = bmax2(mx, __shfl_xor_sync(0xffffffffu, mx, 2));
  mn = bmin2(mn, __shfl_xor_sync(0xffffffffu, mn, 2));
  const float mx0 = bf_lo(mx) * -L, mx1 = bf_hi(mx) * -L, mn0 = bf_lo(mn) * L, mn1 = bf_hi(mn) * L;
#pragma unroll
  for (int i = 0; i < 2; i++) {
    const float a0 = bf_lo(w[2 * i]), a1 = bf_hi(w[2 * i]), b0 = bf_lo(w[2 * i + 1]), b1 = bf_hi(w[2 * i + 1]);
    e[2 * i] = pack_bf(ex2(fmaf(a0, L, mx0)), ex2(fmaf(b0, L, mx0)));
    e[2 * i + 1] = pack_bf(ex2(fmaf(a1, L, mx1)), ex2(fmaf(b1, L, mx1)));
    e[4 + 2 * i] = pack_bf(ex2(fmaf(a0, -L, mn0)), ex2(fmaf(b0, -L, mn0)));
    e[5 + 2 * i] = pack_bf(ex2(fmaf(a1, -L, mn1)), ex2(fmaf(b1, -L, mn1)));
  }
}
__device__ __forceinline__ void norm_store(const uint32_t* e, const float (&s)[4], uint32_t dst) {
  const uint32_t r = pack_bf(rcp(s[0]), rcp(s[2]));
  const __nv_bfloat162 rr = *(const __nv_bfloat162*)&r;
  uint32_t o[4];
#pragma unroll
  for (int i = 0; i < 4; i++) {
    const __nv_bfloat162 v = __hmul2(*(const __nv_bfloat162*)&e[i], (i & 1) ? __high2bfloat162(rr) : __low2bfloat162(rr));
    o[i] = *(const uint32_t*)&v;
  }
  stsm4(dst, o[0], o[1], o[2], o[3]);
}
__host__ __device__ constexpr uint64_t qdesc(uint32_t addr) { return mkdesc(addr, 128, 256, 0); }

__global__ void __launch_bounds__(NTHREADS, 1)
fused_kernel(const Params P, const __grid_constant__ CUtensorMap mx, const __grid_constant__ CUtensorMap mw,
             const __grid_constant__ CUtensorMap mo, const __grid_constant__ CUtensorMap mu,
             const __grid_constant__ CUtensorMap mout, const __grid_constant__ CUtensorMap mw4) {
  constexpr uint32_t sb = SB;
  const int tid = threadIdx.x, lane = tid & 31;
  const int warp = __shfl_sync(0xffffffffu, tid >> 5, 0);
  const int b = blockIdx.x, oct = b >> 3, i8 = b & 7;
  const int rt = oct < 8 ? oct : 15 - oct;
  const int hp = (oct >> 3) * 8 + i8;

  const int wg = warp >> 2, w = warp & 3;
  const int d = b * 4 + ((tid >> 5) & 3);
  if (tid < 384) {
    asm volatile("prefetch.tensormap [%0];" ::"l"(&mu) : "memory");
    asm volatile("prefetch.tensormap [%0];" ::"l"(&mw) : "memory");
    asm volatile("prefetch.tensormap [%0];" ::"l"(&mx) : "memory");
    asm volatile("prefetch.tensormap [%0];" ::"l"(&mw4) : "memory");
  }
  if (warp == 12) {
    if (lane == 0) {
#pragma unroll
      for (int i = 0; i < 9; i++) mbar_init(BAR(i), 1);
      asm volatile("fence.mbarrier_init.release.cluster;" ::: "memory");
    }
    __syncwarp();
    if (lane < 9) mbar_expect(BAR(0) + 8 * lane, lane == 5 ? 65536 : ((lane == 0 || lane > 5) ? 16384 : 28672));
    __syncwarp();
    e_tma3d(sb + OFF_W, &mw, BAR(MB_FULL), hp * 32, 0, 0);
    e_tma2d(sb + OFF_X + 3 * 16384, &mx, BAR(MB_FULL), 0, rt * 256);
  } else if (warp == 13) {
    if (lane == 0) {
#pragma unroll
      for (int i = 9; i < 39; i++) mbar_init(BAR(i), i < MB_EMPTY ? 1 : (i < MB_AUX ? 4 : 8));
      asm volatile("fence.mbarrier_init.release.cluster;" ::: "memory");
    }
    __syncwarp();
    if (lane < 9) mbar_expect(BAR(MB_FULL + 8) + 8 * lane, lane < 8 ? 16384 : 131072);
  }
  const KgenRaw raw = kgen_load(P, d, tid >> 7, lane);
  const unsigned short dsk = __ldg((const unsigned short*)P.Dskip + d);
  const uint32_t tb = sb + OFF_T + w * T_CH;
  const uint32_t kp = wg >= 2 ? sb + OFF_STG0 + 16384 + w * 2048 : ((tb + 127) & ~127u) + wg * 2048;
  const KgenAddr kad = kgen_addr(lane, wg == 3 ? sb + OFF_X + 32768 + w * 2048 : kp);
  if (warp == 12) {
#pragma unroll 1
    for (int kb = 1; kb < 4; kb++) {
      if (kb == U_AT) e_tma5d(sb + OFF_STG0, &mu, BAR(MB_URAW), i8 * 64, oct * 4);
      e_tma3d(sb + OFF_W + kb * 12288, &mw, BAR(MB_FULL) + 8 * kb, hp * 32, kb * 64, 0);
      e_tma2d(sb + OFF_X + (kb < 2 ? kb + 3 : kb - 2) * 16384, &mx, BAR(MB_FULL) + 8 * kb, kb * 64, rt * 256);
    }
    e_prefetch(P.x + (size_t)(rt * 256 + hp * 16) * 512, 16384);
    e_tma4d(sb + OFF_W + 4 * 12288, &mw4, BAR(MB_FULL + 4), hp * 32, 4);
    if (smem_u32(smem_raw) != SB) __trap();
    if (lane == 0) TS1(54);
  }
  float k[5][4], k2048, ksc;
  kgen_unit(raw, kad, blockIdx.y, k, k2048, ksc);
  TS(40 + wg);
  if ((fu(k[0][0]) & fu(k[1][0]) & fu(k[2][0]) & fu(k[3][0]) & fu(k[4][0])) == 0xffffffffu) sts32(kp, 0);
  if (wg == 3) {
    nb_sync(0, 512);
    if (warp == 12) {
      asm volatile("fence.proxy.async.shared::cta;" ::: "memory");
      e_tma2d(sb + OFF_X + 2 * 16384, &mx, BAR(MB_FULL + 4), 256, rt * 256);
    }
  } else if (wg) {
    nb_arrive(0, 512);
  }
  k2048 += __shfl_xor_sync(0xffffffffu, k2048, 16);
  k2048 += __shfl_xor_sync(0xffffffffu, k2048, 8);
  if (wg != 2) {
    uint32_t h[10];
#pragma unroll
    for (int j = 0; j < 10; j++) h[j] = hu(__floats2half2_rn(k[j >> 1][2 * (j & 1)], k[j >> 1][2 * (j & 1) + 1]));
    sts128(kp + lane * 16, h[0], h[1], h[2], h[3]);
    sts128(kp + 512 + lane * 16, h[4], h[5], h[6], h[7]);
    sts128(kp + 1024 + lane * 16, h[8], h[9], fu(k2048), fu(ksc));
  }
  if (wg == 0) { nb_arrive(NB_PREP, 512); nb_sync(0, 512); }
  else if (wg == 3) nb_arrive(NB_PREP, 512);
  else nb_sync(NB_PREP, 512);
  if (warp >= 12) {
    asm volatile("setmaxnreg.dec.sync.aligned.u32 32;");
    if (warp == 12) {
      uint32_t slot = sb + OFF_X + 3 * 16384;
#pragma unroll 1
      for (int n = 0; n < 11; n++) {
        mbar_spin(BAR(MB_EMPTY) + 8 * n);
        const int m = n + 5;
        e_tma2d(slot, &mx, BAR(MB_FULL) + 8 * m, (m & 7) * 64, rt * 256 + (m >> 3) * 128);
        slot = slot == sb + OFF_X + 4 * 16384 ? sb + OFF_X : slot + 16384;
        if (n == 7) e_prefetch(P.wo + (size_t)b * 2048, 4096);
      }
#pragma unroll 1
      for (int i = 0; i < 8; i++) {
        mbar_wait(BAR(MB_EMPTY + 10) + 8 * ((0x54332100u >> (4 * i)) & 7));
        const int w0 = (0x54736210u >> (4 * i)) & 7;
        e_tma3d(sb + OFF_W + w0 * 16384, &mo, BAR(MB_WO), 0, w0 * 64, (hp & 3) * 2);
      }
    } else {
      if (warp == 15) {
        const uint4 v0 = __ldg((const uint4*)P.wphi + hp * 64 + lane), v1 = __ldg((const uint4*)P.wphi + hp * 64 + 32 + lane);
        sts128(sb + OFF_PHI + (lane & 1) * 256 + (lane >> 1) * 16, v0.x, v0.y, v0.z, v0.w);
        sts128(sb + OFF_PHI + 512 + (lane & 1) * 256 + (lane >> 1) * 16, v1.x, v1.y, v1.z, v1.w);
        const uint32_t one = (((lane >> 3) ^ (lane >> 4)) & 1) ? 0u : ((lane & 1) ? 0x3F800000u : 0x3F80u);
        const int q = (lane >> 1) & 3;
        sts128(sb + OFF_EYE + lane * 16, q == 0 ? one : 0u, q == 1 ? one : 0u, q == 2 ? one : 0u, q == 3 ? one : 0u);
        sts64(sb + OFF_ONE + lane * 8, 0x3F803F80u, 0x3F803F80u);
        asm volatile("fence.proxy.async.shared::cta;" ::: "memory");
        nb_arrive(NB_KREAD, 160);
        mbar_wait(BAR(MB_EMPTY + ZERO_STEP));
        uint4* py = P.xs + X_Y + b * 1024 + lane;
#pragma unroll 1
        for (int i = 0; i < 1024; i += 32) st_x(py + i, 0, 0, 0, 0);
        nb_arrive(NB_YZ, 160);
        nb_arrive(NB_ODONE, 320);
        if (lane == 0) TS1(55);
        return;
      }
      uint32_t* const cnt = (uint32_t*)(P.xs + X_CNT) + (warp == 13 ? i8 : 8 + rt) * 32;
      const unsigned target = (ld_x32(cnt) & ~15u) + 16;
      if (warp == 13) {
        uint4* pp = P.xs + X_PART + (hp * 8 + rt) * 144 + lane;
#pragma unroll 1
        for (int i = 0; i < 144; i += 32) if (i + lane < 144) st_x(pp + i, 0, 0, 0, 0);
      }
      nb_sync(warp == 13 ? NB_INIT : NB_ODONE, warp == 13 ? 160 : 320);
      if (lane == 0) TS1(warp == 13 ? 49 : 56);
      asm volatile("fence.proxy.async.shared::cta;" ::: "memory");
      if (lane == 0) asm volatile("red.release.gpu.global.add.u32 [%0], 1;" ::"l"(cnt) : "memory");
      if (lane == 0) TS1(warp == 13 ? 50 : 57);
      const uint32_t* pc = (warp == 13 && (lane & 1)) ? (uint32_t*)(P.xs + X_CNT) + (b >> 4) * 32 : cnt;
#pragma unroll 1
      for (int i = 0; i < SPIN_MAX; i++) {
        unsigned v;
        asm volatile("ld.acquire.gpu.global.u32 %0, [%1];" : "=r"(v) : "l"(pc) : "memory");
        if (__all_sync(0xffffffffu, (int)(v - target) >= 0)) break;
      }
      if (lane == 0) TS1(warp == 13 ? 51 : 58);
      asm volatile("fence.proxy.async.global;" ::: "memory");
      if (warp == 13) {
        mbar_wait(BAR(MB_EMPTY + 11));
        e_expect(BAR(MB_UFULL), 4 * U_CH);
        e_bulk(sb + OFF_U, P.xs + X_UT + b * (U_CH / 4), 4 * U_CH, BAR(MB_UFULL));
      } else {
        const uint4* src = P.xs + X_O + (rt * 4 + (hp >> 2)) * 4096;
        e_expect(BAR(MB_OA), 14336);
        e_bulk(sb + OFF_STG0, src + 3200, 14336, BAR(MB_OA));
        e_expect(BAR(MB_OC), 32768);
        e_bulk(sb + OFF_X + 32768, src, 32768, BAR(MB_OC));
        nb_sync(NB_BDONE, 288);
        asm volatile("fence.proxy.async.shared::cta;" ::: "memory");
        e_expect(BAR(MB_OB), 18432);
        e_bulk(sb + OFF_U, src + 2048, 18432, BAR(MB_OB));
      }
    }
    return;
  }

  const int t = tid & 127;
  const int g = lane >> 2, c = lane & 3;
  {
    if (wg == 2) {
      asm volatile("setmaxnreg.inc.sync.aligned.u32 160;");
#pragma unroll
      for (int j = 0; j < 5; j++) { k[j][0] *= ksc; k[j][1] *= ksc; k[j][2] *= ksc; k[j][3] *= ksc; }
#pragma unroll 1
      for (int q = 0; q < 3; q++) {
        const uint32_t src = (q == 2 ? kp : ((tb + 127) & ~127u) + q * 2048) + lane * 16;
        const uint4 v0 = lds128(src), v1 = lds128(src + 512), v2 = lds128(src + 1024);
        const uint32_t h[10] = {v0.x, v0.y, v0.z, v0.w, v1.x, v1.y, v1.z, v1.w, v2.x, v2.y};
#pragma unroll
        for (int j = 0; j < 10; j++) {
          const float2 f = __half22float2(*(const __half2*)&h[j]);
          k[j >> 1][2 * (j & 1)] = fmaf(f.x, uf(v2.w), k[j >> 1][2 * (j & 1)]);
          k[j >> 1][2 * (j & 1) + 1] = fmaf(f.y, uf(v2.w), k[j >> 1][2 * (j & 1) + 1]);
        }
        k2048 += uf(v2.z);
      }
#pragma unroll
      for (int o2 = 4; o2; o2 >>= 1) k2048 += __shfl_xor_sync(0xffffffffu, k2048, o2);
      if (lane == 0) k[0][0] += bf_lo(dsk);
      __syncwarp();
      if (lane == 0) mbar_arrive(BAR(MB_AUX));
      TS(34);
      build_tables(tb, lane, k, k2048);
      TS(35);
      uint4* const g_y = P.xs + X_Y;
      conv_channel(sb + OFF_U + w * U_CH, tb, lane, g_y + (size_t)d * 256 + lane);
      nb_arrive(NB_BDONE, 288);
      TS(37);
      mbar_wait(BAR(MB_OA));
      const int lam = w * 8 + g;
      const uint4* src = g_y + (size_t)(oct * 32 + c * 8) * 256 + i8 * 32 + lam;
      uint4 v[8];
#pragma unroll 1
      for (int it = 0; it < SPIN_MAX; it++) {
        uint32_t m = 0xffffffffu;
#pragma unroll
        for (int i = 0; i < 8; i++) v[i] = ld_x(src + i * 256);
#pragma unroll
        for (int i = 0; i < 8; i++) m = min(m, v[i].x);
        if (__all_sync(0xffffffffu, m != 0)) break;
      }
      __nv_bfloat16* dst = P.out + (size_t)(i8 * 256 + (lam >> 2) * 16 + (lam & 3) * 2) * 1024 + 512 + oct * 32 + c * 8;
#pragma unroll
      for (int i = 0; i < 8; i++) *(uint4*)(dst + (size_t)((i >> 2) * 128 + ((i >> 1) & 1) * 8 + (i & 1)) * 1024) = tr_row(v, i);
      TS(38);
      GT(63);
      if (w == 0) TSDUMP(32);
      return;
    }
    if (wg == 1) {
      mbar_wait(BAR(MB_URAW));
      TS(48);
      uint4* dst = P.xs + X_UT + (i8 * 64 + g) * (U_CH / 16) + (c & 1) * (U_ODD / 16) + U_PAD / 16 + oct * 8 + w * 2 + (c >> 1);
      uint32_t r[8][4];
#pragma unroll
      for (int i = 0; i < 8; i++) ldsm4t(r[i], sb + OFF_STG0 + w * 4096 + lane * 128 + (((i ^ lane) & 7) << 4));
#pragma unroll
      for (int i = 0; i < 8; i++) dst[i * (U_CH / 2)] = make_uint4(r[i][0], r[i][1], r[i][2], r[i][3]);
      nb_arrive(NB_INIT, 160);
      if (lane == 0) mbar_arrive(BAR(MB_AUX));
      mbar_wait(BAR(MB_EMPTY + 4));
      mbar_spin(BAR(MB_EMPTY + 6));
    }
    TS(wg * 16 + 1);
  }

  float acc[2][48];
  {
    uint32_t fb = BAR(MB_FULL) + 64 * wg;
    uint32_t da = (uint32_t)mkdesc(sb + OFF_X, 16, 0, 0) + (wg ? 1024 : 3072), db = (uint32_t)mkdesc(sb + OFF_W, 4096, 0, 0);
    constexpr uint64_t ha = mkdesc(0, 0, 1024, 1), hb = mkdesc(0, 0, 512, 2);
#pragma unroll 1
    for (int kb = 0; kb < 8; kb++) {
      mbar_spin(fb);
      if (kb == 0) TS(wg * 16 + 2);
      WG_FENCE();
#pragma unroll
      for (int k = 0; k < 4; k++) {
        wgmma_ss_n96(acc[0], ha | (da + 2 * k), hb | (db + 64 * k), k ? 1 : kb);
        wgmma_ss_n96(acc[1], ha | (da + 2 * k + 512), hb | (db + 64 * k), k ? 1 : kb);
      }
      WG_COMMIT();
      WG_WAIT(1);
      if (kb > 0 && lane == 0) mbar_arrive(fb + 8 * (MB_EMPTY - MB_FULL - 1));
      fb += 8; db += 768;
      da = da == (uint32_t)mkdesc(sb + OFF_X + 65536, 16, 0, 0) ? da - 4096 : da + 1024;
    }
    if (wg == 0) nb_sync(NB_KREAD, 160);
    WG_WAIT(0);
    if (lane == 0) mbar_arrive(fb + 8 * (MB_EMPTY - MB_FULL - 1));
    mbar_spin(fb + 8 * (MB_EMPTY - MB_FULL - 1));
  }
  TS(wg * 16 + 3);
  asm volatile("setmaxnreg.inc.sync.aligned.u32 160;");

  constexpr uint32_t stg0 = sb + OFF_STG0, stg1 = sb + OFF_X + 32768;
  uint32_t eq[32], vp[16];
  uint4 af[4], aq[4];
#pragma unroll
  for (int u = 0; u < 4; u++) {
    const float* a = acc[u >> 1] + 16 + 8 * (u & 1);
    af[u] = make_uint4(pack_bf(a[0], a[1]), pack_bf(a[2], a[3]), pack_bf(a[4], a[5]), pack_bf(a[6], a[7]));
    aq[u] = make_uint4(pack_bf(a[-16], a[-15]), pack_bf(a[-14], a[-13]), pack_bf(a[-12], a[-11]), pack_bf(a[-10], a[-9]));
  }
#pragma unroll
  for (int i = 0; i < 16; i++) vp[i] = pack_bf(acc[i >> 3][32 + 2 * (i & 7)], acc[i >> 3][33 + 2 * (i & 7)]);
  uint4* const g_part = P.xs + X_PART;
  uint4* const g_o = P.xs + X_O;
  constexpr uint32_t kvs = stg0;
#pragma unroll 1
  for (int it = 0; it < 2; it++) {
    float p[4][8];
    WG_FENCE();
#pragma unroll
    for (int u = 0; u < 4; u++) wgmma_rs_n16(p[u], af[u], qdesc(sb + OFF_PHI + (u & 1) * 512), 0);
    WG_COMMIT();
    WG_WAIT(0);
#pragma unroll
    for (int u = 0; u < 4; u++) {
      const uint32_t pw[4] = {pack_bf(p[u][0], p[u][2]), pack_bf(p[u][1], p[u][3]), pack_bf(p[u][4], p[u][6]), pack_bf(p[u][5], p[u][7])};
      dual_exp(pw, eq + 8 * u);
    }
    if (it == 0) {
      TS(wg * 16 + 12);
      mbar_wait(BAR(MB_AUX));
      uint32_t sl = (wg ? stg1 : stg0) + w * SLAB + lane * 16;
      asm volatile("" : "+r"(sl));
      float rs[8][4];
      WG_FENCE();
#pragma unroll
      for (int i = 0; i < 8; i++) wgmma_rs_n8(rs[i], make_uint4(eq[4 * i], eq[4 * i + 1], eq[4 * i + 2], eq[4 * i + 3]), qdesc(sb + OFF_ONE), 0);
      WG_COMMIT();
#pragma unroll
      for (int i = 0; i < 4; i++) stsm4(sl + (i >> 1) * 4 * SLAB + 2048 + (i & 1) * 512, vp[4 * i], vp[4 * i + 1], vp[4 * i + 2], vp[4 * i + 3]);
      sts128(sl + (lane >> 4) * (4 * SLAB - 256) + 3072, 0x3F803F80u, 0x3F803F80u, 0x3F803F80u, 0x3F803F80u);
      WG_WAIT(0);
#pragma unroll
      for (int i = 0; i < 8; i++) norm_store(eq + 4 * i, rs[i], sl + (i >> 2) * 4 * SLAB + (i & 3) * 512);
      asm volatile("fence.proxy.async.shared::cta;" ::: "memory");
      if (wg) {
        nb_arrive(NB_ST0, 256);
      } else {
        float kc[20];
        uint4* pp = g_part + (size_t)(hp * 8 + rt) * 144 + t;
        uint32_t* pz = (uint32_t*)(pp - t + 128) + w * 16 + c * 8 + g;
        asm volatile("" : "+l"(pp), "+l"(pz));
#pragma unroll 1
        for (int j = 0; j < 2; j++) {
          if (j) mbar_wait(BAR(MB_UFULL));
          nb_sync(j ? NB_ST0 : NB_WG0, j ? 256 : 128);
          const uint64_t da = qdesc(stg0) - j * ((stg0 - stg1) >> 4);
          WG_FENCE();
#pragma unroll
          for (int s = 0; s < 8; s++) wgmma_ss_n40(kc, da + s * (SLAB >> 4), da + s * (SLAB >> 4) + 128, s ? 1 : j);
          WG_COMMIT();
          WG_WAIT(0);
          TS(6);
        }
        float kv[12];
#pragma unroll
        for (int i = 0; i < 8; i++) kv[i] = w & 2 ? kc[8 + i] : kc[i];
        kv[8] = kc[16]; kv[10] = kc[18];
        st_x(pp, nz(pack_bf(kv[0], kv[1])), pack_bf(kv[2], kv[3]), pack_bf(kv[4], kv[5]), pack_bf(kv[6], kv[7]));
        if (c < 2) st_x32(pz, nz(fu(c ? kv[10] : kv[8])));
        TS(5);
      }
#pragma unroll
      for (int u = 0; u < 4; u++) af[u] = aq[u];
    }
  }
  TS(wg * 16 + 4);
  if (wg == 1) {
    mbar_wait(BAR(MB_UFULL));
    const uint4* ps = g_part + (size_t)hp * 8 * 144 + t;
    const uint32_t* zs = (const uint32_t*)(g_part + (size_t)(hp * 8 + (lane >> 4) * 4) * 144 + 128) + w * 16 + (lane & 15);
    uint4 v[8];
    uint32_t zv[4];
#pragma unroll 1
    for (int it = 0; it < SPIN_MAX; it++) {
#pragma unroll
      for (int i = 0; i < 8; i++) v[i] = ld_x(ps + i * 144);
#pragma unroll
      for (int i = 0; i < 4; i++) zv[i] = ld_x32(zs + i * 576);
      uint32_t m = min(min(zv[0], zv[1]), min(zv[2], zv[3]));
#pragma unroll
      for (int i = 0; i < 8; i++) m = min(m, v[i].x);
      if (__all_sync(0xffffffffu, m != 0)) break;
    }
    float s[8];
    WG_FENCE();
#pragma unroll
    for (int r = 0; r < 8; r++) wgmma_rs_n16(s, v[r], qdesc(sb + OFF_EYE), r);
    WG_COMMIT();
    float zsum = (uf(zv[0]) + uf(zv[1])) + (uf(zv[2]) + uf(zv[3]));
    zsum += __shfl_xor_sync(0xffffffffu, zsum, 16);
    const uint32_t z1 = pack_bf(zsum, 1.f);
    if (lane < 16) sts128(kvs + w * 768 + 512 + lane * 16, z1, z1, z1, z1);
    WG_WAIT(0);
    stsm4(kvs + w * 768 + lane * 16, pack_bf(s[0], s[1]), pack_bf(s[2], s[3]), pack_bf(s[4], s[5]), pack_bf(s[6], s[7]));
    asm volatile("fence.proxy.async.shared::cta;" ::: "memory");
    TS(22);
  }
  nb_sync(NB_KV, 256);
  {
    float n[8][12];
    WG_FENCE();
#pragma unroll
    for (int i = 0; i < 8; i++) wgmma_rs_n24(n[i], make_uint4(eq[4 * i], eq[4 * i + 1], eq[4 * i + 2], eq[4 * i + 3]), qdesc(kvs + (i & 3) * 768), 0);
    WG_COMMIT();
    uint32_t* od = (uint32_t*)(g_o + (size_t)((rt * 4 + wg * 2) * 32 + hp * 2) * 128) + w * 64 + lane;
    WG_WAIT(0);
#pragma unroll
    for (int u = 0; u < 4; u++) {
      float(&np)[12] = n[2 * u];
      const float(&nm)[12] = n[2 * u + 1];
      const float q0 = np[9] * rcp(nm[9]), q1 = np[11] * rcp(nm[11]);
      const float r0 = rcp(fmaf(nm[8], q0, fmaf(np[9], 1e-6f, np[8]))), r1 = rcp(fmaf(nm[10], q1, fmaf(np[11], 1e-6f, np[10])));
#pragma unroll
      for (int i = 0; i < 8; i++) np[i] = fmaf(nm[i], (i & 2) ? q1 : q0, np[i]);
      uint32_t* o = od + (u >> 1) * 16384 + (u & 1) * 512;
      o[0] = pack_bf(np[0] * r0, np[1] * r0);
      o[32] = pack_bf(np[2] * r1, np[3] * r1);
      o[256] = pack_bf(np[4] * r0, np[5] * r0);
      o[288] = pack_bf(np[6] * r1, np[7] * r1);
    }
  }
  TS(wg * 16 + 7);
  nb_arrive(NB_ODONE, 320);
  if (wg) { if (w == 0) TSDUMP(16); return; }
  mbar_wait(BAR(MB_WO));
  mbar_wait(BAR(MB_OA));
  TS(8);
  nb_sync(NB_BDONE, 288);
  TS(9);
  float oc[64];
  {
    constexpr uint64_t ha = mkdesc(0, 0, 128, 0), hb = mkdesc(0, 0, 1024, 1);
    constexpr uint32_t da0 = (uint32_t)mkdesc(stg1, 1024, 0, 0), db0 = (uint32_t)mkdesc(sb + OFF_W, 8192, 0, 0);
#pragma unroll 1
    for (int j = 0; j < 8; j++) {
      const int kb = (j + 7) & 7;
      if ((j & 3) == 1) mbar_spin(j == 1 ? BAR(MB_OC) : BAR(MB_OB));
      WG_FENCE();
#pragma unroll
      for (int k = 0; k < 4; k++) wgmma_ss_n128(oc, ha | (da0 + 512 * kb + 128 * k), hb | (db0 + 1024 * kb + 128 * k), k ? 1 : j);
      WG_COMMIT();
    }
    WG_WAIT(0);
  }
  TS(10);
  nb_sync(NB_WG0, 128);
  const uint32_t ot = sb + OFF_W + w * 4096;
#pragma unroll
  for (int i = 0; i < 16; i += 2)
    stsm4(ot + (i >> 3) * 2048 + (lane & 15) * 128 + (((i + (lane >> 4)) ^ lane) & 7) * 16, pack_bf(oc[4 * i], oc[4 * i + 1]),
          pack_bf(oc[4 * i + 2], oc[4 * i + 3]), pack_bf(oc[4 * i + 4], oc[4 * i + 5]), pack_bf(oc[4 * i + 6], oc[4 * i + 7]));
  asm volatile("fence.proxy.async.shared::cta;" ::: "memory");
  __syncwarp();
  e_store3d(&mout, ot, (rt * 4 + (hp >> 2)) * 64 + w * 16, (hp & 3) * 2);
  TS(wg * 16 + 11);
  GT(61 + wg);
  if (w == 0) TSDUMP(0);
  if (w == 1) TSDUMP(48);
}

typedef CUresult (*EncodeFn)(CUtensorMap*, CUtensorMapDataType, cuuint32_t, void*, const cuuint64_t*, const cuuint64_t*,
                             const cuuint32_t*, const cuuint32_t*, CUtensorMapInterleave, CUtensorMapSwizzle,
                             CUtensorMapL2promotion, CUtensorMapFloatOOBfill);

}

extern "C" void kernel_launch(void* const* d_in, const int* in_sizes, int n_in, void* d_out, int out_size) {
  (void)in_sizes; (void)n_in; (void)out_size;
  void* fn = nullptr;
  cudaDriverEntryPointQueryResult qr;
  cudaGetDriverEntryPoint("cuTensorMapEncodeTiled", &fn, cudaEnableDefault, &qr);
  EncodeFn enc = (EncodeFn)fn;
  CUtensorMap mx, mw, mo, mu, mout, mw4;
  const cuuint32_t es[5] = {1, 1, 1, 1, 1};
  {
    cuuint64_t dims[2] = {512, 2048}, st[1] = {1024};
    cuuint32_t box[2] = {64, 128};
    enc(&mx, CU_TENSOR_MAP_DATA_TYPE_BFLOAT16, 2, d_in[0], dims, st, box, es, CU_TENSOR_MAP_INTERLEAVE_NONE,
        CU_TENSOR_MAP_SWIZZLE_128B, CU_TENSOR_MAP_L2_PROMOTION_L2_128B, CU_TENSOR_MAP_FLOAT_OOB_FILL_NONE);
  }
  {
    cuuint64_t dims[3] = {512, 512, 3}, st[2] = {3072, 1024};
    cuuint32_t box[3] = {32, 64, 3};
    enc(&mw, CU_TENSOR_MAP_DATA_TYPE_BFLOAT16, 3, d_in[1], dims, st, box, es, CU_TENSOR_MAP_INTERLEAVE_NONE,
        CU_TENSOR_MAP_SWIZZLE_64B, CU_TENSOR_MAP_L2_PROMOTION_L2_128B, CU_TENSOR_MAP_FLOAT_OOB_FILL_NONE);
  }
  {
    cuuint64_t dims[3] = {64, 512, 8}, st[2] = {1024, 128};
    cuuint32_t box[3] = {64, 64, 2};
    enc(&mo, CU_TENSOR_MAP_DATA_TYPE_BFLOAT16, 3, d_in[3], dims, st, box, es, CU_TENSOR_MAP_INTERLEAVE_NONE,
        CU_TENSOR_MAP_SWIZZLE_128B, CU_TENSOR_MAP_L2_PROMOTION_L2_128B, CU_TENSOR_MAP_FLOAT_OOB_FILL_NONE);
  }
  {
    cuuint64_t dims[5] = {512, 2, 4, 4, 64}, st[4] = {1024, 8192, 2048, 32768};
    cuuint32_t box[5] = {64, 2, 4, 4, 4};
    enc(&mu, CU_TENSOR_MAP_DATA_TYPE_BFLOAT16, 5, d_in[4], dims, st, box, es, CU_TENSOR_MAP_INTERLEAVE_NONE,
        CU_TENSOR_MAP_SWIZZLE_128B, CU_TENSOR_MAP_L2_PROMOTION_L2_128B, CU_TENSOR_MAP_FLOAT_OOB_FILL_NONE);
  }
  {
    cuuint64_t dims[3] = {64, 2048, 16}, st[2] = {2048, 128};
    cuuint32_t box[3] = {64, 16, 2};
    enc(&mout, CU_TENSOR_MAP_DATA_TYPE_BFLOAT16, 3, d_out, dims, st, box, es, CU_TENSOR_MAP_INTERLEAVE_NONE,
        CU_TENSOR_MAP_SWIZZLE_128B, CU_TENSOR_MAP_L2_PROMOTION_NONE, CU_TENSOR_MAP_FLOAT_OOB_FILL_NONE);
  }
  {
    cuuint64_t dims[4] = {512, 64, 3, 8}, st[3] = {3072, 1024, 64 * 3072};
    cuuint32_t box[4] = {32, 64, 3, 4};
    enc(&mw4, CU_TENSOR_MAP_DATA_TYPE_BFLOAT16, 4, d_in[1], dims, st, box, es, CU_TENSOR_MAP_INTERLEAVE_NONE,
        CU_TENSOR_MAP_SWIZZLE_64B, CU_TENSOR_MAP_L2_PROMOTION_L2_128B, CU_TENSOR_MAP_FLOAT_OOB_FILL_NONE);
  }
  Params P;
  P.x = (const __nv_bfloat16*)d_in[0];
  P.wphi = (const __nv_bfloat16*)d_in[2];
  P.wo = (const __nv_bfloat16*)d_in[3];
  P.logA = (const __nv_bfloat16*)d_in[5];
  P.Aim = (const __nv_bfloat16*)d_in[6];
  P.Cre = (const __nv_bfloat16*)d_in[7];
  P.Cim = (const __nv_bfloat16*)d_in[8];
  P.logdt = (const __nv_bfloat16*)d_in[9];
  P.Dskip = (const __nv_bfloat16*)d_in[10];
  P.out = (__nv_bfloat16*)d_out;
  cudaGetSymbolAddress((void**)&P.xs, g_x);
  P.ts = nullptr;
  cudaFuncSetAttribute(fused_kernel, cudaFuncAttributeMaxDynamicSharedMemorySize, SMEM_BYTES);
  fused_kernel<<<NCTA, NTHREADS, SMEM_BYTES>>>(P, mx, mw, mo, mu, mout, mw4);
}
```

```cpp
#include <cuda_runtime.h>
#include <cuda_bf16.h>
#include <cuda_fp16.h>
#include <cuda.h>
#include <stdint.h>

#define DBG_TS 0

namespace {

constexpr int NTHREADS = 512;
constexpr int NCTA = 128;
constexpr int OFF_W = 0;
constexpr int OFF_X = 98304;
constexpr int OFF_U = OFF_X + 65536;
constexpr int U_CH = 4416, U_ODD = 2240, U_PAD = 128;
constexpr int OFF_STG0 = OFF_U + 18432;
constexpr int SLAB = 3328;
constexpr int OFF_T = OFF_STG0 + 8 * SLAB;
constexpr int T_CH = 5216;
constexpr int T_D = 0;
constexpr int T_5 = 2144;
constexpr int T_3 = T_5 + 384;
constexpr int T_7 = T_5 + 1024;
constexpr int T_9 = T_7 + 320;
constexpr int T_KC = T_9 + 320;
constexpr int T_ST = T_5 - 1024;
constexpr int OFF_PHI = OFF_T + 4 * T_CH;
constexpr int OFF_EYE = OFF_PHI + 1024, OFF_ONE = OFF_EYE + 512;
constexpr int OFF_BAR = OFF_ONE + 256;
constexpr int SMEM_BYTES = OFF_BAR + 512 + 256 * DBG_TS;
constexpr uint32_t SB = 1024;
static_assert(T_KC + 2 * 656 <= T_CH, "table size");
static_assert(SMEM_BYTES <= 232448, "smem");
constexpr int MB_URAW = 0, MB_FULL = 1  , MB_WO = 17, MB_UFULL = 18, MB_OA = 19, MB_OB = 20, MB_OC = 21,
              MB_EMPTY = 22  , MB_AUX = 38;
__host__ __device__ constexpr uint32_t BAR(int i) { return SB + OFF_BAR + 8 * i; }
constexpr int NB_WG0 = 1, NB_ODONE = 2, NB_ST0 = 3  , NB_KV = 5, NB_YZ = 6, NB_INIT = 7, NB_PREP = 8, NB_PROD = 9, NB_KREAD = 10, NB_BDONE = 11, NB_ZERO = 12;
#define U_AT 2
#define ZERO_STEP 15
constexpr int SPIN_MAX = 1 << 16;

constexpr int X_CNT = 0;
constexpr int X_PART = 128;
constexpr int X_O = X_PART + 16 * 8 * 144;
constexpr int X_Y = X_O + 32 * 32 * 128;
constexpr int X_UT = X_Y + 512 * 8 * 32;
constexpr int X_SIZE = X_UT + 512 * (U_CH / 16);
__device__ __align__(128) uint4 g_x[X_SIZE];
extern __shared__ uint8_t smem_raw[];
#define TS(i) do {} while (0)
#define TS1(i) do {} while (0)
#define GT(i) do {} while (0)
#define TSDUMP(base) do {} while (0)

__device__ __forceinline__ uint32_t smem_u32(const void* p) { return (uint32_t)__cvta_generic_to_shared(p); }
__device__ __forceinline__ void mbar_arrive(uint32_t b) {
  asm volatile("mbarrier.arrive.shared::cta.b64 _, [%0];" ::"r"(b) : "memory");
}
__device__ __forceinline__ void mbar_wait(uint32_t b) {
  uint32_t done = 0;
#pragma unroll 1
  for (int i = 0; i < SPIN_MAX && !done; i++) {
    asm volatile("{\n.reg .pred p;\nmbarrier.try_wait.parity.shared::cta.b64 p, [%1], 0, 4000;\nselp.u32 %0, 1, 0, p;\n}\n"
                 : "=r"(done) : "r"(b) : "memory");
  }
}
__device__ __forceinline__ void mbar_spin(uint32_t b) {
  uint32_t done = 0;
#pragma unroll 1
  for (int i = 0; i < (SPIN_MAX << 4) && !done; i++) {
    asm volatile("{\n.reg .pred p;\nmbarrier.try_wait.parity.shared::cta.b64 p, [%1], 0;\nselp.u32 %0, 1, 0, p;\n}\n"
                 : "=r"(done) : "r"(b) : "memory");
  }
}
__device__ __forceinline__ void mbar_init(uint32_t b, int n) {
  asm volatile("mbarrier.init.shared::cta.b64 [%0], %1;" ::"r"(b), "r"(n) : "memory");
}
__device__ __forceinline__ void mbar_expect(uint32_t b, int bytes) {
  asm volatile("mbarrier.arrive.expect_tx.shared::cta.b64 _, [%0], %1;" ::"r"(b), "r"(bytes) : "memory");
}
__device__ __forceinline__ void nb_sync(int id, int n) { asm volatile("bar.sync %0, %1;" ::"r"(id), "r"(n) : "memory"); }
__device__ __forceinline__ void nb_arrive(int id, int n) { asm volatile("bar.arrive %0, %1;" ::"r"(id), "r"(n) : "memory"); }
#define ELECT "{\n.reg .pred p;\nelect.sync _|p, 0xffffffff;\n@p "
__device__ __forceinline__ void e_expect(uint32_t b, int bytes) {
  asm volatile(ELECT "mbarrier.arrive.expect_tx.shared::cta.b64 _, [%0], %1;\n}\n" ::"r"(b), "r"(bytes) : "memory");
}
__device__ __forceinline__ void e_tma2d(uint32_t dst, const CUtensorMap* m, uint32_t bar, int c0, int c1) {
  asm volatile(ELECT "cp.async.bulk.tensor.2d.shared::cluster.global.mbarrier::complete_tx::bytes [%0], [%1, {%3,%4}], [%2];\n}\n"
               ::"r"(dst), "l"(m), "r"(bar), "r"(c0), "r"(c1) : "memory");
}
__device__ __forceinline__ void e_tma3d(uint32_t dst, const CUtensorMap* m, uint32_t bar, int c0, int c1, int c2) {
  asm volatile(ELECT "cp.async.bulk.tensor.3d.shared::cluster.global.mbarrier::complete_tx::bytes [%0], [%1, {%3,%4,%5}], [%2];\n}\n"
               ::"r"(dst), "l"(m), "r"(bar), "r"(c0), "r"(c1), "r"(c2) : "memory");
}
__device__ __forceinline__ void e_tma4d(uint32_t dst, const CUtensorMap* m, uint32_t bar, int c0, int c3) {
  asm volatile(ELECT "cp.async.bulk.tensor.4d.shared::cluster.global.mbarrier::complete_tx::bytes [%0], [%1, {%3,%5,%5,%4}], [%2];\n}\n"
               ::"r"(dst), "l"(m), "r"(bar), "r"(c0), "r"(c3), "r"(0) : "memory");
}
__device__ __forceinline__ void e_tma5d(uint32_t dst, const CUtensorMap* m, uint32_t bar, int c0, int c4) {
  asm volatile(ELECT "cp.async.bulk.tensor.5d.shared::cluster.global.mbarrier::complete_tx::bytes [%0], [%1, {%3,%5,%5,%5,%4}], [%2];\n}\n"
               ::"r"(dst), "l"(m), "r"(bar), "r"(c0), "r"(c4), "r"(0) : "memory");
}
__device__ __forceinline__ void e_bulk(uint32_t dst, const void* src, int bytes, uint32_t bar) {
  asm volatile(ELECT "cp.async.bulk.shared::cluster.global.mbarrier::complete_tx::bytes [%0], [%1], %2, [%3];\n}\n"
               ::"r"(dst), "l"(src), "r"(bytes), "r"(bar) : "memory");
}
__device__ __forceinline__ void e_prefetch(const void* p, int bytes) {
  asm volatile(ELECT "cp.async.bulk.prefetch.L2.global [%0], %1;\n}\n" ::"l"(p), "r"(bytes) : "memory");
}
__device__ __forceinline__ void e_store3d(const CUtensorMap* m, uint32_t src, int c1, int c2) {
  asm volatile(ELECT "cp.async.bulk.tensor.3d.global.shared::cta.bulk_group [%0, {%4,%2,%3}], [%1];\n"
               "@p cp.async.bulk.commit_group;\n@p cp.async.bulk.wait_group.read 0;\n}\n"
               ::"l"(m), "r"(src), "r"(c1), "r"(c2), "r"(0) : "memory");
}
__host__ __device__ constexpr uint64_t mkdesc(uint32_t addr, uint32_t lbo, uint32_t sbo, int swz) {
  return (uint64_t)((addr & 0x3FFFF) >> 4) | ((uint64_t)(lbo >> 4) << 16) | ((uint64_t)(sbo >> 4) << 32) |
         ((uint64_t)swz << 62);
}
#define WG_FENCE() asm volatile("wgmma.fence.sync.aligned;" ::: "memory")
#define WG_COMMIT() asm volatile("wgmma.commit_group.sync.aligned;" ::: "memory")
#define WG_WAIT(n) asm volatile("wgmma.wait_group.sync.aligned " #n ";" ::: "memory")

__device__ __forceinline__ void mma(float& d0, float& d1, float& d2, float& d3, uint32_t a0, uint32_t a1, uint32_t a2,
                                    uint32_t a3, uint32_t b0, uint32_t b1) {
  asm volatile("mma.sync.aligned.m16n8k16.row.col.f32.bf16.bf16.f32 {%0,%1,%2,%3},{%4,%5,%6,%7},{%8,%9},{%0,%1,%2,%3};"
               : "+f"(d0), "+f"(d1), "+f"(d2), "+f"(d3)
               : "r"(a0), "r"(a1), "r"(a2), "r"(a3), "r"(b0), "r"(b1));
}
__device__ __forceinline__ void mmac(float (&d)[4], uint32_t a0, uint32_t a1, uint32_t a2, uint32_t a3, uint32_t b0,
                                     uint32_t b1, const float (&c)[4]) {
  asm volatile("mma.sync.aligned.m16n8k16.row.col.f32.bf16.bf16.f32 {%0,%1,%2,%3},{%4,%5,%6,%7},{%8,%9},{%10,%11,%12,%13};"
               : "=f"(d[0]), "=f"(d[1]), "=f"(d[2]), "=f"(d[3])
               : "r"(a0), "r"(a1), "r"(a2), "r"(a3), "r"(b0), "r"(b1), "f"(c[0]), "f"(c[1]), "f"(c[2]), "f"(c[3]));
}
__device__ __forceinline__ void mma_p(int p, float (&d)[4], uint32_t a0, uint32_t a1, uint32_t a2, uint32_t a3, uint32_t b0, uint32_t b1) {
  asm volatile("{\n.reg .pred q;\nsetp.ne.b32 q, %10, 0;\n"
               "@q mma.sync.aligned.m16n8k16.row.col.f32.bf16.bf16.f32 {%0,%1,%2,%3},{%4,%5,%6,%7},{%8,%9},{%0,%1,%2,%3};\n}\n"
               : "+f"(d[0]), "+f"(d[1]), "+f"(d[2]), "+f"(d[3])
               : "r"(a0), "r"(a1), "r"(a2), "r"(a3), "r"(b0), "r"(b1), "r"(p));
}
__device__ __forceinline__ void mmac_p(int p, float (&d)[4], uint32_t a0, uint32_t a1, uint32_t a2, uint32_t a3, uint32_t b0,
                                       uint32_t b1, const float (&c)[4]) {
  asm volatile("{\n.reg .pred q;\nsetp.ne.b32 q, %14, 0;\n"
               "@q mma.sync.aligned.m16n8k16.row.col.f32.bf16.bf16.f32 {%0,%1,%2,%3},{%4,%5,%6,%7},{%8,%9},{%10,%11,%12,%13};\n}\n"
               : "+f"(d[0]), "+f"(d[1]), "+f"(d[2]), "+f"(d[3])
               : "r"(a0), "r"(a1), "r"(a2), "r"(a3), "r"(b0), "r"(b1), "f"(c[0]), "f"(c[1]), "f"(c[2]), "f"(c[3]), "r"(p));
}
__device__ __forceinline__ void mma_h(float (&d)[4], const uint32_t (&a)[4], uint32_t b0, uint32_t b1) {
  asm volatile("mma.sync.aligned.m16n8k16.row.col.f32.f16.f16.f32 {%0,%1,%2,%3},{%4,%5,%6,%7},{%8,%9},{%0,%1,%2,%3};"
               : "+f"(d[0]), "+f"(d[1]), "+f"(d[2]), "+f"(d[3]) : "r"(a[0]), "r"(a[1]), "r"(a[2]), "r"(a[3]), "r"(b0), "r"(b1));
}
__device__ __forceinline__ void mma0(float& d0, float& d1, float& d2, float& d3, uint32_t a0, uint32_t a1, uint32_t a2,
                                     uint32_t a3, uint32_t b0, uint32_t b1) {
  asm volatile("mma.sync.aligned.m16n8k16.row.col.f32.bf16.bf16.f32 {%0,%1,%2,%3},{%4,%5,%6,%7},{%8,%9},{%10,%10,%10,%10};"
               : "=f"(d0), "=f"(d1), "=f"(d2), "=f"(d3)
               : "r"(a0), "r"(a1), "r"(a2), "r"(a3), "r"(b0), "r"(b1), "f"(0.f));
}
__device__ __forceinline__ uint32_t pack_bf(float lo, float hi) {
  uint32_t r;
  asm("cvt.rn.bf16x2.f32 %0, %1, %2;" : "=r"(r) : "f"(hi), "f"(lo));
  return r;
}
__device__ __forceinline__ float bf_lo(uint32_t w) { return __uint_as_float(w << 16); }
__device__ __forceinline__ float bf_hi(uint32_t w) { return __uint_as_float(w & 0xffff0000u); }
__device__ __forceinline__ float bf_round(float x) { return __bfloat162float(__float2bfloat16_rn(x)); }
__device__ __forceinline__ uint32_t bmax2(uint32_t a, uint32_t b) {
  uint32_t r; asm("max.bf16x2 %0, %1, %2;" : "=r"(r) : "r"(a), "r"(b)); return r;
}
__device__ __forceinline__ uint32_t bmin2(uint32_t a, uint32_t b) {
  uint32_t r; asm("min.bf16x2 %0, %1, %2;" : "=r"(r) : "r"(a), "r"(b)); return r;
}
__device__ __forceinline__ float ex2(float x) { float r; asm("ex2.approx.ftz.f32 %0, %1;" : "=f"(r) : "f"(x)); return r; }
__device__ __forceinline__ float rcp(float x) { float r; asm("rcp.approx.ftz.f32 %0, %1;" : "=f"(r) : "f"(x)); return r; }
__device__ __forceinline__ void ldsm4(uint32_t (&r)[4], uint32_t a) {
  asm volatile("ldmatrix.sync.aligned.m8n8.x4.shared.b16 {%0,%1,%2,%3}, [%4];"
               : "=r"(r[0]), "=r"(r[1]), "=r"(r[2]), "=r"(r[3]) : "r"(a) : "memory");
}
__device__ __forceinline__ void ldsm4t(uint32_t (&r)[4], uint32_t a) {
  asm volatile("ldmatrix.sync.aligned.m8n8.x4.trans.shared.b16 {%0,%1,%2,%3}, [%4];"
               : "=r"(r[0]), "=r"(r[1]), "=r"(r[2]), "=r"(r[3]) : "r"(a) : "memory");
}
__device__ __forceinline__ void stsm4(uint32_t a, uint32_t r0, uint32_t r1, uint32_t r2, uint32_t r3) {
  asm volatile("stmatrix.sync.aligned.m8n8.x4.shared.b16 [%0], {%1,%2,%3,%4};"
               ::"r"(a), "r"(r0), "r"(r1), "r"(r2), "r"(r3) : "memory");
}
__device__ __forceinline__ uint32_t lds32(uint32_t a) {
  uint32_t r; asm volatile("ld.shared.u32 %0, [%1];" : "=r"(r) : "r"(a) : "memory"); return r;
}
__device__ __forceinline__ uint32_t lds16(uint32_t a) {
  uint32_t r; asm volatile("{\n.reg .u16 h;\nld.shared.u16 h, [%1];\ncvt.u32.u16 %0, h;\n}\n" : "=r"(r) : "r"(a) : "memory"); return r;
}
__device__ __forceinline__ uint2 lds64(uint32_t a) {
  uint2 r; asm volatile("ld.shared.v2.u32 {%0,%1}, [%2];" : "=r"(r.x), "=r"(r.y) : "r"(a) : "memory"); return r;
}
__device__ __forceinline__ uint4 lds128(uint32_t a) {
  uint4 r;
  asm volatile("ld.shared.v4.u32 {%0,%1,%2,%3}, [%4];" : "=r"(r.x), "=r"(r.y), "=r"(r.z), "=r"(r.w) : "r"(a) : "memory");
  return r;
}
__device__ __forceinline__ void sts32(uint32_t a, uint32_t v) { asm volatile("st.shared.u32 [%0], %1;" ::"r"(a), "r"(v) : "memory"); }
__device__ __forceinline__ void sts16(uint32_t a, uint32_t v) {
  asm volatile("{\n.reg .u16 h;\ncvt.u16.u32 h, %1;\nst.shared.u16 [%0], h;\n}\n" ::"r"(a), "r"(v) : "memory");
}
__device__ __forceinline__ void sts64(uint32_t a, uint32_t x, uint32_t y) {
  asm volatile("st.shared.v2.u32 [%0], {%1,%2};" ::"r"(a), "r"(x), "r"(y) : "memory");
}
__device__ __forceinline__ void sts128(uint32_t a, uint32_t x, uint32_t y, uint32_t z, uint32_t w) {
  asm volatile("st.shared.v4.u32 [%0], {%1,%2,%3,%4};" ::"r"(a), "r"(x), "r"(y), "r"(z), "r"(w) : "memory");
}
__device__ __forceinline__ uint4 ld_x(const uint4* p) {
  uint4 r;
  asm volatile("{\n.reg .b128 t;\nld.relaxed.gpu.global.b128 t, [%4];\nmov.b128 {%0,%1,%2,%3}, t;\n}\n"
               : "=r"(r.x), "=r"(r.y), "=r"(r.z), "=r"(r.w) : "l"(p) : "memory");
  return r;
}
__device__ __forceinline__ uint32_t ld_x32(const uint32_t* p) {
  uint32_t r; asm volatile("ld.relaxed.gpu.global.u32 %0, [%1];" : "=r"(r) : "l"(p) : "memory"); return r;
}
__device__ __forceinline__ void st_x(uint4* p, uint32_t x, uint32_t y, uint32_t z, uint32_t w) {
  asm volatile("{\n.reg .b128 t;\nmov.b128 t, {%1,%2,%3,%4};\nst.relaxed.gpu.global.b128 [%0], t;\n}\n"
               ::"l"(p), "r"(x), "r"(y), "r"(z), "r"(w) : "memory");
}
__device__ __forceinline__ void st_x_p(int p, uint4* a, uint32_t x, uint32_t y, uint32_t z, uint32_t w) {
  asm volatile("{\n.reg .b128 t;\n.reg .pred q;\nsetp.ne.b32 q, %5, 0;\nmov.b128 t, {%1,%2,%3,%4};\n@q st.relaxed.gpu.global.b128 [%0], t;\n}\n"
               ::"l"(a), "r"(x), "r"(y), "r"(z), "r"(w), "r"(p) : "memory");
}
__device__ __forceinline__ void sts64_p(int p, uint32_t a, uint32_t x, uint32_t y) {
  asm volatile("{\n.reg .pred q;\nsetp.ne.b32 q, %3, 0;\n@q st.shared.v2.u32 [%0], {%1,%2};\n}\n" ::"r"(a), "r"(x), "r"(y), "r"(p) : "memory");
}
__device__ __forceinline__ void st_x32(uint32_t* p, uint32_t x) {
  asm volatile("st.relaxed.gpu.global.u32 [%0], %1;" ::"l"(p), "r"(x) : "memory");
}
__device__ __forceinline__ uint32_t nz(uint32_t w) { return max(w, 1u); }
__device__ __forceinline__ uint32_t fu(float x) { return __float_as_uint(x); }
__device__ __forceinline__ float uf(uint32_t x) { return __uint_as_float(x); }

__device__ __forceinline__ void wgmma_ss_n96(float (&d)[48], uint64_t da, uint64_t db, int sc) {
  asm volatile("{\n.reg .pred p;\nsetp.ne.b32 p, %50, 0;\n"
      "wgmma.mma_async.sync.aligned.m64n96k16.f32.bf16.bf16 "
      "{%0,%1,%2,%3,%4,%5,%6,%7,%8,%9,%10,%11,%12,%13,%14,%15,%16,%17,%18,%19,%20,%21,%22,%23,%24,%25,%26,%27,%28,%29,%30,%31,%32,%33,%34,%35,%36,%37,%38,%39,%40,%41,%42,%43,%44,%45,%46,%47}, "
      "%48, %49, p, 1, 1, 0, 1;\n}\n"
      : "+f"(d[0]), "+f"(d[1]), "+f"(d[2]), "+f"(d[3]), "+f"(d[4]), "+f"(d[5]), "+f"(d[6]), "+f"(d[7]),
        "+f"(d[8]), "+f"(d[9]), "+f"(d[10]), "+f"(d[11]), "+f"(d[12]), "+f"(d[13]), "+f"(d[14]), "+f"(d[15]),
        "+f"(d[16]), "+f"(d[17]), "+f"(d[18]), "+f"(d[19]), "+f"(d[20]), "+f"(d[21]), "+f"(d[22]), "+f"(d[23]),
        "+f"(d[24]), "+f"(d[25]), "+f"(d[26]), "+f"(d[27]), "+f"(d[28]), "+f"(d[29]), "+f"(d[30]), "+f"(d[31]),
        "+f"(d[32]), "+f"(d[33]), "+f"(d[34]), "+f"(d[35]), "+f"(d[36]), "+f"(d[37]), "+f"(d[38]), "+f"(d[39]),
        "+f"(d[40]), "+f"(d[41]), "+f"(d[42]), "+f"(d[43]), "+f"(d[44]), "+f"(d[45]), "+f"(d[46]), "+f"(d[47])
      : "l"(da), "l"(db), "r"(sc));
}

__device__ __forceinline__ void wgmma_ss_n128(float (&d)[64], uint64_t da, uint64_t db, int sc) {
  asm volatile("{\n.reg .pred p;\nsetp.ne.b32 p, %66, 0;\n"
      "wgmma.mma_async.sync.aligned.m64n128k16.f32.bf16.bf16 "
      "{%0,%1,%2,%3,%4,%5,%6,%7,%8,%9,%10,%11,%12,%13,%14,%15,%16,%17,%18,%19,%20,%21,%22,%23,%24,%25,%26,%27,%28,%29,%30,%31,%32,%33,%34,%35,%36,%37,%38,%39,%40,%41,%42,%43,%44,%45,%46,%47,%48,%49,%50,%51,%52,%53,%54,%55,%56,%57,%58,%59,%60,%61,%62,%63}, "
      "%64, %65, p, 1, 1, 0, 1;\n}\n"
      : "+f"(d[0]), "+f"(d[1]), "+f"(d[2]), "+f"(d[3]), "+f"(d[4]), "+f"(d[5]), "+f"(d[6]), "+f"(d[7]),
        "+f"(d[8]), "+f"(d[9]), "+f"(d[10]), "+f"(d[11]), "+f"(d[12]), "+f"(d[13]), "+f"(d[14]), "+f"(d[15]),
        "+f"(d[16]), "+f"(d[17]), "+f"(d[18]), "+f"(d[19]), "+f"(d[20]), "+f"(d[21]), "+f"(d[22]), "+f"(d[23]),
        "+f"(d[24]), "+f"(d[25]), "+f"(d[26]), "+f"(d[27]), "+f"(d[28]), "+f"(d[29]), "+f"(d[30]), "+f"(d[31]),
        "+f"(d[32]), "+f"(d[33]), "+f"(d[34]), "+f"(d[35]), "+f"(d[36]), "+f"(d[37]), "+f"(d[38]), "+f"(d[39]),
        "+f"(d[40]), "+f"(d[41]), "+f"(d[42]), "+f"(d[43]), "+f"(d[44]), "+f"(d[45]), "+f"(d[46]), "+f"(d[47]),
        "+f"(d[48]), "+f"(d[49]), "+f"(d[50]), "+f"(d[51]), "+f"(d[52]), "+f"(d[53]), "+f"(d[54]), "+f"(d[55]),
        "+f"(d[56]), "+f"(d[57]), "+f"(d[58]), "+f"(d[59]), "+f"(d[60]), "+f"(d[61]), "+f"(d[62]), "+f"(d[63])
      : "l"(da), "l"(db), "r"(sc));
}

__device__ __forceinline__ void wgmma_ss_n40(float (&d)[20], uint64_t da, uint64_t db, int sc) {
  asm volatile("{\n.reg .pred p;\nsetp.ne.b32 p, %22, 0;\n"
      "wgmma.mma_async.sync.aligned.m64n40k16.f32.bf16.bf16 "
      "{%0,%1,%2,%3,%4,%5,%6,%7,%8,%9,%10,%11,%12,%13,%14,%15,%16,%17,%18,%19}, "
      "%20, %21, p, 1, 1, 1, 1;\n}\n"
      : "+f"(d[0]), "+f"(d[1]), "+f"(d[2]), "+f"(d[3]), "+f"(d[4]), "+f"(d[5]), "+f"(d[6]), "+f"(d[7]),
        "+f"(d[8]), "+f"(d[9]), "+f"(d[10]), "+f"(d[11]), "+f"(d[12]), "+f"(d[13]), "+f"(d[14]), "+f"(d[15]),
        "+f"(d[16]), "+f"(d[17]), "+f"(d[18]), "+f"(d[19])
      : "l"(da), "l"(db), "r"(sc));
}

__device__ __forceinline__ void wgmma_rs_n8(float (&d)[4], const uint4& a, uint64_t db, int sc) {
  asm volatile("{\n.reg .pred p;\nsetp.ne.b32 p, %9, 0;\n"
      "wgmma.mma_async.sync.aligned.m64n8k16.f32.bf16.bf16 "
      "{%0,%1,%2,%3}, "
      "{%4,%5,%6,%7}, %8, p, 1, 1, 1;\n}\n"
      : "+f"(d[0]), "+f"(d[1]), "+f"(d[2]), "+f"(d[3])
      : "r"(a.x), "r"(a.y), "r"(a.z), "r"(a.w), "l"(db), "r"(sc));
}

__device__ __forceinline__ void wgmma_rs_n16(float (&d)[8], const uint4& a, uint64_t db, int sc) {
  asm volatile("{\n.reg .pred p;\nsetp.ne.b32 p, %13, 0;\n"
      "wgmma.mma_async.sync.aligned.m64n16k16.f32.bf16.bf16 "
      "{%0,%1,%2,%3,%4,%5,%6,%7}, "
      "{%8,%9,%10,%11}, %12, p, 1, 1, 1;\n}\n"
      : "+f"(d[0]), "+f"(d[1]), "+f"(d[2]), "+f"(d[3]), "+f"(d[4]), "+f"(d[5]), "+f"(d[6]), "+f"(d[7])
      : "r"(a.x), "r"(a.y), "r"(a.z), "r"(a.w), "l"(db), "r"(sc));
}

__device__ __forceinline__ void wgmma_rs_n24(float (&d)[12], const uint4& a, uint64_t db, int sc) {
  asm volatile("{\n.reg .pred p;\nsetp.ne.b32 p, %17, 0;\n"
      "wgmma.mma_async.sync.aligned.m64n24k16.f32.bf16.bf16 "
      "{%0,%1,%2,%3,%4,%5,%6,%7,%8,%9,%10,%11}, "
      "{%12,%13,%14,%15}, %16, p, 1, 1, 1;\n}\n"
      : "+f"(d[0]), "+f"(d[1]), "+f"(d[2]), "+f"(d[3]), "+f"(d[4]), "+f"(d[5]), "+f"(d[6]), "+f"(d[7]),
        "+f"(d[8]), "+f"(d[9]), "+f"(d[10]), "+f"(d[11])
      : "r"(a.x), "r"(a.y), "r"(a.z), "r"(a.w), "l"(db), "r"(sc));
}

struct Params {
  const __nv_bfloat16 *logA, *Aim, *Cre, *Cim, *logdt, *Dskip, *x, *wphi, *wo;
  __nv_bfloat16* out;
  uint4* xs;
  long long* ts;
};

__device__ __forceinline__ uint4 tr_row(const uint4 (&v)[8], int i) {
  uint32_t o[4];
#pragma unroll
  for (int m = 0; m < 4; m++) {
    const uint4 &ra = v[2 * m], &rb = v[2 * m + 1];
    const int k = i >> 1;
    const uint32_t xa = k == 0 ? ra.x : k == 1 ? ra.y : k == 2 ? ra.z : ra.w;
    const uint32_t xb = k == 0 ? rb.x : k == 1 ? rb.y : k == 2 ? rb.z : rb.w;
    o[m] = __byte_perm(xa, xb, (i & 1) ? 0x7632 : 0x5410);
  }
  return make_uint4(o[0], o[1], o[2], o[3]);
}

struct cpx { float r, i; };
__device__ __forceinline__ cpx csq(cpx a) { return {a.r * a.r - a.i * a.i, 2.f * (a.r * a.i)}; }
__device__ __forceinline__ cpx polar(float e, float t) {
  const float m = ex2(e);
  return {m * __cosf(t), m * __sinf(t)};
}

struct KgenRaw { unsigned short la, ai, cr, ci, ldt; };
__device__ __forceinline__ KgenRaw kgen_load(const Params& P, int d, int unit, int lane) {
  const int o = d * 128 + unit * 32 + lane;
  return {__ldg((const unsigned short*)P.logA + o), __ldg((const unsigned short*)P.Aim + o), __ldg((const unsigned short*)P.Cre + o),
          __ldg((const unsigned short*)P.Cim + o), __ldg((const unsigned short*)P.logdt + d)};
}
struct hmul { __half2 a, b; };
__device__ __forceinline__ hmul mk_mul(cpx w) {
  uint32_t b;
  asm("{\n.reg .f32 n;\nneg.ftz.f32 n, %1;\ncvt.rn.f16x2.f32 %0, %2, n;\n}\n" : "=r"(b) : "f"(w.i), "f"(w.r));
  return {__floats2half2_rn(w.r, w.i), *(const __half2*)&b};
}
__device__ __forceinline__ __half2 hcm(__half2 z, const hmul& w) { return __hfma2(__high2half2(z), w.b, __hmul2(__low2half2(z), w.a)); }
__device__ __forceinline__ uint32_t hu(__half2 v) { return *(const uint32_t*)&v; }

struct KgenAddr { uint32_t sa, sb, lb, lc, la; };
__device__ __forceinline__ KgenAddr kgen_addr(int lane, uint32_t buf) {
  KgenAddr a;
  a.sa = buf + (lane & 7) * 128 + ((((lane >> 3) ^ lane) & 7) << 4);
  a.lb = buf + (lane >> 3) * 128 + (((lane ^ (lane >> 3)) & 7) << 4);
  a.la = buf + ((lane >> 3) & 1) * 1024 + (lane >> 4) * 128 + (((lane ^ (lane >> 4)) & 7) << 4);
  a.sb = a.sa ^ 64; a.lc = a.lb ^ 64;
  asm volatile("" : "+r"(a.sa), "+r"(a.sb), "+r"(a.lb), "+r"(a.lc), "+r"(a.la));
  return a;
}
__device__ __forceinline__ void kgen_unit(const KgenRaw& r, const KgenAddr& ad, uint32_t zero, float (&k)[5][4], float& k2048, float& sc) {
  const float dt = bf_round(expf(bf_lo(r.ldt)));
  const float a2 = bf_round(ex2(bf_lo(r.la) * 1.4426950408889634f)) * (dt * -1.4426950408889634f);
  const float f = bf_lo(r.ai) * dt;
  const float r128 = f * 20.371832715762604f;
  const uint32_t ex = min(max(__reduce_max_sync(0xffffffffu, max(r.cr & 0x7fffu, r.ci & 0x7fffu)) >> 7, 1u), 253u);
  const float cs = uf((254u - ex) << 23);
  sc = 2.f * dt * uf(ex << 23);
  const cpx C = {bf_lo(r.cr) * cs, -bf_lo(r.ci) * cs};
  auto put = [&](const __half2 (&v)[8], uint32_t off) {
    stsm4(ad.sa + off, hu(v[0]), hu(v[1]), hu(v[2]), hu(v[3]));
    stsm4(ad.sb + off, hu(v[4]), hu(v[5]), hu(v[6]), hu(v[7]));
  };
  uint32_t A[4][4], B[5][2][4];
  auto get = [&](int j, uint32_t off) {
    __syncwarp();
    ldsm4(B[j][0], ad.lb + off);
    ldsm4(B[j][1], ad.lc + 512 + off);
  };
  auto tile = [&](int j) {
    k[j][0] = k[j][1] = k[j][2] = k[j][3] = 0.f;
#pragma unroll
    for (int s = 0; s < 4; s++) mma_h(k[j], A[s], B[j][s >> 1][2 * (s & 1)], B[j][s >> 1][2 * (s & 1) + 1]);
  };
  auto after = [&](cpx v, uint32_t dep) { return cpx{uf(fu(v.r) ^ (dep & zero)), v.i}; };
  const cpx w1 = polar(a2, f), w128 = polar(a2 * 128.f, (r128 - rintf(r128)) * 6.283185307179586f);
  const cpx w2 = csq(w1), w4 = csq(w2);
  __half2 t0[8], t1[8], t2[8], t3[8], t4[8];
  const hmul m2 = mk_mul(w2), m4 = mk_mul(w4), m128 = mk_mul(w128);
  t0[0] = __floats2half2_rn(1.f, 0.f); t0[1] = __floats2half2_rn(w1.r, w1.i); t0[2] = m2.a; t0[4] = m4.a;
  t0[3] = hcm(t0[1], m2); t0[5] = hcm(t0[1], m4); t0[6] = hcm(t0[2], m4); t0[7] = hcm(t0[3], m4);
  put(t0, 0); get(0, 0);
  t1[0] = m128.a;
#pragma unroll
  for (int i = 1; i < 8; i++) t1[i] = hcm(t0[i], m128);
  put(t1, 1024); get(1, 1024);
  {
    cpx w8 = csq(after(w4, B[0][0][0]));
    w8.i = -w8.i;
    const cpx w16 = csq(w8), w32 = csq(w16), w64 = csq(w32);
    const hmul m8 = mk_mul(w8), m16 = mk_mul(w16), m32 = mk_mul(w32), m64 = mk_mul(w64);
    __half2 a[8];
    a[0] = __floats2half2_rn(C.r, C.i); a[1] = hcm(a[0], m8);
    a[2] = hcm(a[0], m16); a[3] = hcm(a[1], m16);
#pragma unroll
    for (int i = 0; i < 4; i++) a[4 + i] = hcm(a[i], m32);
    put(a, 0);
#pragma unroll
    for (int i = 0; i < 8; i++) a[i] = hcm(a[i], m64);
    put(a, 1024);
    __syncwarp();
#pragma unroll
    for (int s = 0; s < 4; s++) ldsm4(A[s], (ad.la ^ (s << 5)) + s * 256);
  }
  const cpx w256 = csq(after(w128, B[1][0][0]));
  const hmul m256 = mk_mul(w256);
  t2[0] = m256.a;
#pragma unroll
  for (int i = 1; i < 8; i++) t2[i] = hcm((i & 1) ? t1[i & 6] : t0[i & 6], m256);
  put(t2, 0); get(2, 0);
  tile(0); tile(1);
  const cpx w512 = csq(after(w256, A[0][0]));
  const hmul m512 = mk_mul(w512);
  t3[0] = m512.a;
#pragma unroll
  for (int i = 1; i < 8; i++) t3[i] = hcm((i & 2) ? t2[i & 5] : ((i & 1) ? t1[i & 4] : t0[i & 4]), m512);
  put(t3, 1024); get(3, 1024);
  tile(2);
  const cpx w1024 = csq(after(w512, B[2][0][0])), we = csq(w1024);
  const hmul m1024 = mk_mul(w1024);
  t4[0] = m1024.a;
#pragma unroll
  for (int i = 1; i < 8; i++) t4[i] = hcm((i & 4) ? t3[i & 3] : ((i & 2) ? t2[i & 1] : t1[0]), m1024);
  put(t4, 0); get(4, 0);
  tile(3); tile(4);
  k2048 = (C.r * we.r + C.i * we.i) * sc;
}

__device__ __forceinline__ void build_tables(uint32_t tb, int lane, float (&k)[5][4], float k2048) {
  const int g = lane >> 2, c = lane & 3;
  const uint32_t kc = tb + T_KC + 16;
  {
    const uint32_t a0 = kc + 16 * g + 4 * c, a2 = kc + 2 * (256 + 4 * g + c);
    const uint32_t a3 = kc + 2 * (384 + 2 * g + 64 * (c & 1) + (c >> 1)), a4 = kc + 2 * (512 + g + 32 * c);
#pragma unroll
    for (int r = 0; r < 2; r++) {
      sts32(a0 + 128 * r, pack_bf(k[0][2 * r], k[0][2 * r + 1]));
      sts32(a0 + 128 * r + 256, pack_bf(k[1][2 * r], k[1][2 * r + 1]));
      const uint32_t w2 = pack_bf(k[2][2 * r], k[2][2 * r + 1]);
      const uint32_t w3 = pack_bf(k[3][2 * r], k[3][2 * r + 1]);
      const uint32_t w4 = pack_bf(k[4][2 * r], k[4][2 * r + 1]);
      sts16(a2 + 64 * r, w2); sts16(a2 + 64 * r + 128, w2 >> 16);
      sts16(a3 + 32 * r, w3); sts16(a3 + 32 * r + 64, w3 >> 16);
      sts16(a4 + 16 * r, w4); sts16(a4 + 16 * r + 32, w4 >> 16);
    }
  }
  if (lane == 0) { sts16(kc + 2 * 640, pack_bf(k2048, 0.f)); sts16(kc - 2, 0); }
  __syncwarp();
  const uint32_t td = tb + T_D + 32;
  {
    const uint4 v = lds128(kc + 16 * lane);
    const uint32_t pv = lds16(kc + 16 * lane - 2);
    sts128(td + 32 * lane, __byte_perm(v.x, pv, 0x5410), __byte_perm(v.x, v.x, 0x1032), __byte_perm(v.y, v.x, 0x7610),
           __byte_perm(v.y, v.y, 0x1032));
    sts128(td + 32 * lane + 16, __byte_perm(v.z, v.y, 0x7610), __byte_perm(v.z, v.z, 0x1032),
           __byte_perm(v.w, v.z, 0x7610), __byte_perm(v.w, v.w, 0x1032));
  }
  {
    const uint2 v = lds64(kc + 512 + 8 * lane);
    const uint32_t k4 = lds16(kc + 512 + 8 * lane + 8);
    const uint32_t pv = lds16(kc + (lane == 0 ? 510 : 512 + 8 * lane));
    const uint32_t k22 = __byte_perm(v.y, v.y, 0x1010);
    sts128(td + 1024 + 32 * lane, __byte_perm(v.x, pv, 0x5410), __byte_perm(v.x, v.x, 0x1010),
           __byte_perm(v.x, v.x, 0x1032), __byte_perm(v.y, v.x, 0x7610));
    sts128(td + 1024 + 32 * lane + 16, k22, k22, __byte_perm(v.y, v.y, 0x1032), __byte_perm(k4, v.y, 0x7610));
  }
  {
    const uint32_t kk = lds16(kc + 2 * 384);
    const uint32_t w = lane < 3 ? (kk | (kk << 16)) : (lane == 3 ? (kk << 16) : 0u);
    if (lane < 24) sts32(td + 4 * (lane < 16 ? 512 + lane : lane - 24), w);
    const uint32_t lo_ = lds16(kc + 2 * 511), le_ = lds16(kc + 2 * 512);
    const uint32_t ja = tb + T_5 + (lane < 16 ? 4 * lane : 256 + 4 * lane);
    sts32(ja, lane == 16 ? (le_ << 16) : 0u);
    sts32(ja + 384, lane == 16 ? (lo_ << 16) : 0u);
    sts32(tb + (lane < 16 ? T_7 : T_9 - 64) + 4 * lane, 0u);
  }
#pragma unroll
  for (int s = 0; s < 2; s++) {
    const uint32_t b = kc + 2 * (s ? 512 : 384) + 8 * lane;
    const uint2 v = lds64(b);
    uint32_t em = lds16(b - 2), e0 = v.x;
    const uint32_t e4 = lds16(b + 8);
    if (lane == 0) { em = 0; e0 = 0; }
    sts64(tb + (s ? T_7 : T_3) + 64 + 8 * lane, __byte_perm(v.x, em, 0x5432), __byte_perm(v.y, v.x, 0x7632));
    sts64(tb + (s ? T_9 : T_5) + 64 + 8 * lane, __byte_perm(v.y, e0, 0x5410), __byte_perm(e4, v.y, 0x5410));
  }
  __syncwarp();
}

__device__ __forceinline__ uint32_t box2w(int lo, int n, int o) {
  return ((unsigned)(o - lo) < (unsigned)n ? 0x3F80u : 0u) | ((unsigned)(o + 1 - lo) < (unsigned)n ? 0x3F800000u : 0u);
}

#define SPLIT() asm volatile("{\n.reg .pred p;\nsetp.ne.u32 p, %0, 0;\n@p exit;\n}\n" ::"r"(blockIdx.y) : "memory")

__device__ __forceinline__ void conv_channel(uint32_t ub, uint32_t tb, int lane, uint4* ydst) {
  const int g = lane >> 2, c = lane & 3, x = g - 2 * c;
  const int mi = lane >> 3;
  const uint32_t qa = ub + U_PAD + 16 * (lane & 7) + ((mi == 0 || mi == 3) ? U_ODD : 0) - (mi == 0 ? 16 : 0);
  const uint32_t hb = ub + U_PAD + (mi & 1) * U_ODD + 16 * ((lane >> 4) + (lane & 7)) - 16;
  const uint32_t kv = lds16(tb + T_KC + 16 + 2 * 512);
  const int oh = c < 2 ? 8 + 2 * c : 2 * c - 8, og = c < 3 ? 2 * c : -10;
  uint32_t bx[4] = {box2w(g - 4, 9, 2 * c), box2w(g - 3, 7, 2 * c), box2w(g - 4, 9, oh), box2w(g - 3, 7, oh)};
  uint32_t by[4] = {box2w(g - 10, 5, 2 * c - 8), box2w(g - 5, 3, 2 * c - 8), box2w(g - 10, 5, og), box2w(g - 5, 3, og)};
  uint32_t lb0 = ((unsigned)(x + 5) < 2u ? kv : 0u) | ((unsigned)(x + 4) < 2u ? kv << 16 : 0u);
  uint32_t lb1 = ((unsigned)(x - 3) < 2u ? kv : 0u) | ((unsigned)(x - 4) < 2u ? kv << 16 : 0u);
  const int q0 = g - 1, q1 = c < 3 ? g : g - 2;
  uint32_t y0a = ub + U_PAD + (q0 & 1) * U_ODD + 16 * (q0 >> 1) + 4 * c;
  uint32_t y1a = ub + U_PAD + (q1 & 1) * U_ODD + 16 * (q1 >> 1) + 4 * c;
  uint32_t f3[3][4][4];
  {
    const uint32_t fa = tb + T_7 + 4 * (16 + x);
#pragma unroll
    for (int tt = 0; tt < 3; tt++)
#pragma unroll
      for (int D = 0; D < 4; D++) {
        const uint32_t a = fa + (tt == 0 ? 316 : (tt == 1 ? 320 : 0)) + 64 * D;
        f3[tt][D][0] = lds32(a); f3[tt][D][1] = lds32(a + 32); f3[tt][D][2] = lds32(a - 32); f3[tt][D][3] = lds32(a);
      }
  }
#pragma unroll
  for (int i = 0; i < 4; i++) asm volatile("" : "+r"(bx[i]), "+r"(by[i]));
  asm volatile("" : "+r"(lb0), "+r"(lb1), "+r"(y0a), "+r"(y1a));
  mbar_wait(BAR(MB_UFULL));
  mbar_wait(BAR(MB_EMPTY + 15));
  TS(36);
  float acc[16][4];
  {
    uint32_t z09[8], z07[8], zm9[8], zm7[8];
#pragma unroll
    for (int i = 0; i < 8; i++) {
      uint32_t h[4];
      ldsm4(h, hb + 128 * i);
      float y0, y1, y2, y3, w0, w1, w2, w3;
      mma0(y0, y1, y2, y3, bx[0], bx[1], bx[2], bx[3], h[2], c < 2 ? h[3] : h[1]);
      mma0(w0, w1, w2, w3, bx[0], bx[1], bx[2], bx[3], h[1], c < 2 ? h[2] : h[0]);
      z09[i] = pack_bf(y0, y1); z07[i] = pack_bf(y2, y3);
      zm9[i] = pack_bf(w0, w1); zm7[i] = pack_bf(w2, w3);
    }
    float a[4][2][4];
#pragma unroll
    for (int kap = 0; kap < 4; kap++)
#pragma unroll
      for (int sg = 0; sg < 2; sg++)
#pragma unroll
        for (int bk = 3; bk >= kap; bk--) {
          const uint32_t(&q0_)[4] = f3[sg ? 2 : 0][bk - kap];
          const uint32_t(&q1_)[4] = f3[sg ? 2 : 1][bk - kap];
          float(&a0)[4] = a[bk][0];
          float(&a1)[4] = a[bk][1];
          if (sg == 0 && kap == 0) {
            mma0(a0[0], a0[1], a0[2], a0[3], q0_[0], q0_[1], q0_[2], q0_[3], z09[0], z09[1]);
            mma0(a1[0], a1[1], a1[2], a1[3], q1_[0], q1_[1], q1_[2], q1_[3], zm9[0], zm9[1]);
          } else {
            mma(a0[0], a0[1], a0[2], a0[3], q0_[0], q0_[1], q0_[2], q0_[3], sg ? zm7[2 * kap] : z09[2 * kap], sg ? zm7[2 * kap + 1] : z09[2 * kap + 1]);
            mma(a1[0], a1[1], a1[2], a1[3], q1_[0], q1_[1], q1_[2], q1_[3], sg ? z07[2 * kap] : zm9[2 * kap], sg ? z07[2 * kap + 1] : zm9[2 * kap + 1]);
          }
        }
    SPLIT();
#pragma unroll
    for (int i = 0; i < 8; i++) {
      uint32_t h[4];
      ldsm4(h, qa + 128 * i);
      const float ci[4] = {a[i >> 1][0][2 * (i & 1)], a[i >> 1][0][2 * (i & 1) + 1], a[i >> 1][1][2 * (i & 1)], a[i >> 1][1][2 * (i & 1) + 1]};
      mmac(acc[8 + i], h[0], h[1], h[2], h[3], lb0, lb1, ci);
    }
  }
  TS(44);
  {
    uint2 a5[10], a3[10];
    const uint32_t aa = tb + T_5 + 4 * (8 + 2 * g - 2 * c);
#pragma unroll
    for (int m = 0; m < 10; m++) { a5[m] = lds64(aa + 32 * m); a3[m] = lds64(aa + 384 + 32 * m); }
    uint32_t x5[12][2], x3[12][2];
    auto ygen = [&](int kap) {
#pragma unroll
      for (int hh = 0; hh < 2; hh++) {
        float y0, y1, y2, y3;
        mma0(y0, y1, y2, y3, by[0], by[1], by[2], by[3], lds32(y0a + 128 * kap + 64 * hh), lds32(y1a + 128 * kap + 64 * hh));
        x5[kap][hh] = pack_bf(y0, y1);
        x3[kap][hh] = pack_bf(y2, y3);
      }
    };
    ygen(11); ygen(10); ygen(9); ygen(8);
#pragma unroll
    for (int kap = 11; kap >= 0; kap--) {
      if (kap >= 4) ygen(kap - 4);
#pragma unroll
      for (int sg = 0; sg < 2; sg++)
#pragma unroll
        for (int i = 4; i >= 0; i--) {
          const int be = kap + 4 + i;
          if (be <= 15) {
            const uint2 &hi = sg ? a3[2 * i + 1] : a5[2 * i + 1], &lo = sg ? a3[2 * i] : a5[2 * i];
            const uint32_t b0 = sg ? x3[kap][0] : x5[kap][0], b1 = sg ? x3[kap][1] : x5[kap][1];
            if (be < 8 && i == 0 && sg == 0) mma0(acc[be][0], acc[be][1], acc[be][2], acc[be][3], hi.x, hi.y, lo.x, lo.y, b0, b1);
            else mma(acc[be][0], acc[be][1], acc[be][2], acc[be][3], hi.x, hi.y, lo.x, lo.y, b0, b1);
          }
        }
    }
  }
  TS(45);
  {
    const uint32_t st = tb + T_ST + lane * 8;
#pragma unroll
    for (int be = 4; be < 12; be++) sts64(st + 256 * be, pack_bf(acc[be][0], acc[be][1]), pack_bf(acc[be][2], acc[be][3]));
    SPLIT();
    uint32_t F[66], qd[8][4];
    const uint32_t fa = tb + T_D + 32 + 4 * x;
#pragma unroll
    for (int i = 0; i < 32; i++) {
      const int s = 120 - (i >> 2) - 8 * (i & 3);
      uint32_t(&q)[4] = qd[i & 7];
      ldsm4(q, qa + 16 * s);
      const int m = 16 * (i & 3) + 2 * (i >> 2);
      F[m] = lds32(fa + 32 * m); F[m + 1] = lds32(fa + 32 * m + 32);
#pragma unroll
      for (int be = 15; be >= 12; be--) {
        const int de = 8 * be - s;
        if (de >= 0) mma(acc[be][0], acc[be][1], acc[be][2], acc[be][3], q[0], q[1], q[2], q[3], F[2 * de + 1], F[2 * de]);
      }
    }
    F[64] = lds32(fa + 32 * 64); F[65] = lds32(fa + 32 * 65);
    uint32_t qp = qa + 128 * 11, sta = st + 256 * 10;
    uint4* yd = ydst + 7 * 32;
#pragma unroll
    for (int i = 0; i < 6; i++) ldsm4(qd[i], qp - 16 * i);
    uint2 sv = lds64(sta + 256);
    float ci[4] = {bf_lo(sv.x), bf_hi(sv.x), bf_lo(sv.y), bf_hi(sv.y)};
    float T[5][4];
#pragma unroll
    for (int i = 0; i < 16; i++) T[i >> 2][i & 3] = acc[12 + (i >> 2)][i & 3];
    nb_sync(NB_YZ, 160);
    TS(46);
#pragma unroll 1
    for (int bp = 5; bp >= 0; bp--) {
      uint32_t held[2];
#pragma unroll
      for (int o = 1; o >= 0; o--) {
#pragma unroll
        for (int k = 4; k >= 1; k--) mmac(T[k], qd[0][0], qd[0][1], qd[0][2], qd[0][3], F[16 * k + 1], F[16 * k], T[k - 1]);
        mmac(T[0], qd[0][0], qd[0][1], qd[0][2], qd[0][3], F[1], F[0], ci);
        ldsm4(qd[6], qp - 16 * 6);
        ldsm4(qd[7], qp - 16 * 7);
        sv = lds64(sta);
#pragma unroll
        for (int i = 1; i < 8; i++) {
#pragma unroll
          for (int k = 3; k >= 0; k--)
            mma(T[k][0], T[k][1], T[k][2], T[k][3], qd[i][0], qd[i][1], qd[i][2], qd[i][3], F[16 * k + 2 * i + 1], F[16 * k + 2 * i]);
          if (i < 7) ldsm4(qd[i - 1], qp - 128 - 16 * (i - 1));
          if (i == 2) {
            const uint32_t w0 = pack_bf(T[4][0], T[4][1]), w1 = pack_bf(T[4][2], T[4][3]);
            if (o) { held[0] = w0; held[1] = w1; }
            else st_x(yd, nz(w0), w1, held[0], held[1]);
          }
          if (i == 4) {
            if (2 * bp + o <= 4) sv = make_uint2(0, 0);
            ci[0] = bf_lo(sv.x); ci[1] = bf_hi(sv.x); ci[2] = bf_lo(sv.y); ci[3] = bf_hi(sv.y);
          }
        }
        qp -= 128; sta -= 256;
      }
      yd -= 32;
    }
#pragma unroll
    for (int B = 1; B >= 0; B--)
      st_x(ydst + B * 32, nz(pack_bf(T[2 * B][0], T[2 * B][1])), pack_bf(T[2 * B][2], T[2 * B][3]),
           pack_bf(T[2 * B + 1][0], T[2 * B + 1][1]), pack_bf(T[2 * B + 1][2], T[2 * B + 1][3]));
  }
}

__device__ __forceinline__ void dual_exp(const uint32_t* w, uint32_t* e) {
  const float L = 1.44268798828125f;
  uint32_t mx = bmax2(bmax2(w[0], w[1]), bmax2(w[2], w[3]));
  uint32_t mn = bmin2(bmin2(w[0], w[1]), bmin2(w[2], w[3]));
  mx = bmax2(mx, __shfl_xor_sync(0xffffffffu, mx, 1));
  mn = bmin2(mn, __shfl_xor_sync(0xffffffffu, mn, 1));
  mx = bmax2(mx, __shfl_xor_sync(0xffffffffu, mx, 2));
  mn = bmin2(mn, __shfl_xor_sync(0xffffffffu, mn, 2));
  const float mx0 = bf_lo(mx) * -L, mx1 = bf_hi(mx) * -L, mn0 = bf_lo(mn) * L, mn1 = bf_hi(mn) * L;
#pragma unroll
  for (int i = 0; i < 2; i++) {
    const float a0 = bf_lo(w[2 * i]), a1 = bf_hi(w[2 * i]), b0 = bf_lo(w[2 * i + 1]), b1 = bf_hi(w[2 * i + 1]);
    e[2 * i] = pack_bf(ex2(fmaf(a0, L, mx0)), ex2(fmaf(b0, L, mx0)));
    e[2 * i + 1] = pack_bf(ex2(fmaf(a1, L, mx1)), ex2(fmaf(b1, L, mx1)));
    e[4 + 2 * i] = pack_bf(ex2(fmaf(a0, -L, mn0)), ex2(fmaf(b0, -L, mn0)));
    e[5 + 2 * i] = pack_bf(ex2(fmaf(a1, -L, mn1)), ex2(fmaf(b1, -L, mn1)));
  }
}
__device__ __forceinline__ void norm_store(const uint32_t* e, const float (&s)[4], uint32_t dst) {
  const uint32_t r = pack_bf(rcp(s[0]), rcp(s[2]));
  const __nv_bfloat162 rr = *(const __nv_bfloat162*)&r;
  uint32_t o[4];
#pragma unroll
  for (int i = 0; i < 4; i++) {
    const __nv_bfloat162 v = __hmul2(*(const __nv_bfloat162*)&e[i], (i & 1) ? __high2bfloat162(rr) : __low2bfloat162(rr));
    o[i] = *(const uint32_t*)&v;
  }
  stsm4(dst, o[0], o[1], o[2], o[3]);
}
__host__ __device__ constexpr uint64_t qdesc(uint32_t addr) { return mkdesc(addr, 128, 256, 0); }

__global__ void __launch_bounds__(NTHREADS, 1)
fused_kernel(const Params P, const __grid_constant__ CUtensorMap mx, const __grid_constant__ CUtensorMap mw,
             const __grid_constant__ CUtensorMap mo, const __grid_constant__ CUtensorMap mu,
             const __grid_constant__ CUtensorMap mout, const __grid_constant__ CUtensorMap mw4) {
  constexpr uint32_t sb = SB;
  const int tid = threadIdx.x, lane = tid & 31;
  const int warp = __shfl_sync(0xffffffffu, tid >> 5, 0);
  const int b = blockIdx.x, oct = b >> 3, i8 = b & 7;
  const int rt = oct < 8 ? oct : 15 - oct;
  const int hp = (oct >> 3) * 8 + i8;

  const int wg = warp >> 2, w = warp & 3;
  const int d = b * 4 + ((tid >> 5) & 3);
  if (tid < 384) {
    asm volatile("prefetch.tensormap [%0];" ::"l"(&mu) : "memory");
    asm volatile("prefetch.tensormap [%0];" ::"l"(&mw) : "memory");
    asm volatile("prefetch.tensormap [%0];" ::"l"(&mx) : "memory");
    asm volatile("prefetch.tensormap [%0];" ::"l"(&mw4) : "memory");
  }
  if (warp == 12) {
    if (lane == 0) {
#pragma unroll
      for (int i = 0; i < 9; i++) mbar_init(BAR(i), 1);
      asm volatile("fence.mbarrier_init.release.cluster;" ::: "memory");
    }
    __syncwarp();
    if (lane < 9) mbar_expect(BAR(0) + 8 * lane, lane == 5 ? 65536 : ((lane == 0 || lane > 5) ? 16384 : 28672));
    __syncwarp();
    e_tma3d(sb + OFF_W, &mw, BAR(MB_FULL), hp * 32, 0, 0);
    e_tma2d(sb + OFF_X + 3 * 16384, &mx, BAR(MB_FULL), 0, rt * 256);
  } else if (warp == 13) {
    if (lane == 0) {
#pragma unroll
      for (int i = 9; i < 39; i++) mbar_init(BAR(i), i < MB_EMPTY ? 1 : (i < MB_AUX ? 4 : 8));
      asm volatile("fence.mbarrier_init.release.cluster;" ::: "memory");
    }
    __syncwarp();
    if (lane < 9) mbar_expect(BAR(MB_FULL + 8) + 8 * lane, lane < 8 ? 16384 : 131072);
  }
  const KgenRaw raw = kgen_load(P, d, tid >> 7, lane);
  const unsigned short dsk = __ldg((const unsigned short*)P.Dskip + d);
  const uint32_t tb = sb + OFF_T + w * T_CH;
  const uint32_t kp = wg >= 2 ? sb + OFF_STG0 + 16384 + w * 2048 : ((tb + 127) & ~127u) + wg * 2048;
  const KgenAddr kad = kgen_addr(lane, wg == 3 ? sb + OFF_X + 32768 + w * 2048 : kp);
  if (warp == 12) {
#pragma unroll 1
    for (int kb = 1; kb < 4; kb++) {
      if (kb == U_AT) e_tma5d(sb + OFF_STG0, &mu, BAR(MB_URAW), i8 * 64, oct * 4);
      e_tma3d(sb + OFF_W + kb * 12288, &mw, BAR(MB_FULL) + 8 * kb, hp * 32, kb * 64, 0);
      e_tma2d(sb + OFF_X + (kb < 2 ? kb + 3 : kb - 2) * 16384, &mx, BAR(MB_FULL) + 8 * kb, kb * 64, rt * 256);
    }
    e_prefetch(P.x + (size_t)(rt * 256 + hp * 16) * 512, 16384);
    e_tma4d(sb + OFF_W + 4 * 12288, &mw4, BAR(MB_FULL + 4), hp * 32, 4);
    if (smem_u32(smem_raw) != SB) __trap();
    if (lane == 0) TS1(54);
  }
  float k[5][4], k2048, ksc;
  kgen_unit(raw, kad, blockIdx.y, k, k2048, ksc);
  TS(40 + wg);
  if ((fu(k[0][0]) & fu(k[1][0]) & fu(k[2][0]) & fu(k[3][0]) & fu(k[4][0])) == 0xffffffffu) sts32(kp, 0);
  if (wg == 3) {
    nb_sync(0, 512);
    if (warp == 12) {
      asm volatile("fence.proxy.async.shared::cta;" ::: "memory");
      e_tma2d(sb + OFF_X + 2 * 16384, &mx, BAR(MB_FULL + 4), 256, rt * 256);
    }
  } else if (wg) {
    nb_arrive(0, 512);
  }
  k2048 += __shfl_xor_sync(0xffffffffu, k2048, 16);
  k2048 += __shfl_xor_sync(0xffffffffu, k2048, 8);
  if (wg != 2) {
    uint32_t h[10];
#pragma unroll
    for (int j = 0; j < 10; j++) h[j] = hu(__floats2half2_rn(k[j >> 1][2 * (j & 1)], k[j >> 1][2 * (j & 1) + 1]));
    sts128(kp + lane * 16, h[0], h[1], h[2], h[3]);
    sts128(kp + 512 + lane * 16, h[4], h[5], h[6], h[7]);
    sts128(kp + 1024 + lane * 16, h[8], h[9], fu(k2048), fu(ksc));
  }
  if (wg == 0) { nb_arrive(NB_PREP, 512); nb_sync(0, 512); }
  else if (wg == 3) nb_arrive(NB_PREP, 512);
  else nb_sync(NB_PREP, 512);
  if (warp >= 12) {
    asm volatile("setmaxnreg.dec.sync.aligned.u32 32;");
    if (warp == 12) {
      uint32_t slot = sb + OFF_X + 3 * 16384;
#pragma unroll 1
      for (int n = 0; n < 11; n++) {
        mbar_spin(BAR(MB_EMPTY) + 8 * n);
        const int m = n + 5;
        e_tma2d(slot, &mx, BAR(MB_FULL) + 8 * m, (m & 7) * 64, rt * 256 + (m >> 3) * 128);
        slot = slot == sb + OFF_X + 4 * 16384 ? sb + OFF_X : slot + 16384;
        if (n == 7) e_prefetch(P.wo + (size_t)b * 2048, 4096);
      }
#pragma unroll 1
      for (int i = 0; i < 8; i++) {
        mbar_wait(BAR(MB_EMPTY + 10) + 8 * ((0x54332100u >> (4 * i)) & 7));
        const int w0 = (0x54736210u >> (4 * i)) & 7;
        e_tma3d(sb + OFF_W + w0 * 16384, &mo, BAR(MB_WO), 0, w0 * 64, (hp & 3) * 2);
      }
    } else {
      if (warp == 15) {
        const uint4 v0 = __ldg((const uint4*)P.wphi + hp * 64 + lane), v1 = __ldg((const uint4*)P.wphi + hp * 64 + 32 + lane);
        sts128(sb + OFF_PHI + (lane & 1) * 256 + (lane >> 1) * 16, v0.x, v0.y, v0.z, v0.w);
        sts128(sb + OFF_PHI + 512 + (lane & 1) * 256 + (lane >> 1) * 16, v1.x, v1.y, v1.z, v1.w);
        const uint32_t one = (((lane >> 3) ^ (lane >> 4)) & 1) ? 0u : ((lane & 1) ? 0x3F800000u : 0x3F80u);
        const int q = (lane >> 1) & 3;
        sts128(sb + OFF_EYE + lane * 16, q == 0 ? one : 0u, q == 1 ? one : 0u, q == 2 ? one : 0u, q == 3 ? one : 0u);
        sts64(sb + OFF_ONE + lane * 8, 0x3F803F80u, 0x3F803F80u);
        asm volatile("fence.proxy.async.shared::cta;" ::: "memory");
        nb_arrive(NB_KREAD, 160);
        mbar_wait(BAR(MB_EMPTY + ZERO_STEP));
        uint4* py = P.xs + X_Y + b * 1024 + lane;
#pragma unroll 1
        for (int i = 0; i < 1024; i += 32) st_x(py + i, 0, 0, 0, 0);
        nb_arrive(NB_YZ, 160);
        nb_arrive(NB_ODONE, 320);
        if (lane == 0) TS1(55);
        return;
      }
      uint32_t* const cnt = (uint32_t*)(P.xs + X_CNT) + (warp == 13 ? i8 : 8 + rt) * 32;
      const unsigned target = (ld_x32(cnt) & ~15u) + 16;
      if (warp == 13) {
        uint4* pp = P.xs + X_PART + (hp * 8 + rt) * 144 + lane;
#pragma unroll 1
        for (int i = 0; i < 144; i += 32) if (i + lane < 144) st_x(pp + i, 0, 0, 0, 0);
      }
      nb_sync(warp == 13 ? NB_INIT : NB_ODONE, warp == 13 ? 160 : 320);
      if (lane == 0) TS1(warp == 13 ? 49 : 56);
      asm volatile("fence.proxy.async.shared::cta;" ::: "memory");
      if (lane == 0) asm volatile("red.release.gpu.global.add.u32 [%0], 1;" ::"l"(cnt) : "memory");
      if (lane == 0) TS1(warp == 13 ? 50 : 57);
      const uint32_t* pc = (warp == 13 && (lane & 1)) ? (uint32_t*)(P.xs + X_CNT) + (b >> 4) * 32 : cnt;
#pragma unroll 1
      for (int i = 0; i < SPIN_MAX; i++) {
        unsigned v;
        asm volatile("ld.acquire.gpu.global.u32 %0, [%1];" : "=r"(v) : "l"(pc) : "memory");
        if (__all_sync(0xffffffffu, (int)(v - target) >= 0)) break;
      }
      if (lane == 0) TS1(warp == 13 ? 51 : 58);
      asm volatile("fence.proxy.async.global;" ::: "memory");
      if (warp == 13) {
        mbar_wait(BAR(MB_EMPTY + 11));
        e_expect(BAR(MB_UFULL), 4 * U_CH);
        e_bulk(sb + OFF_U, P.xs + X_UT + b * (U_CH / 4), 4 * U_CH, BAR(MB_UFULL));
      } else {
        const uint4* src = P.xs + X_O + (rt * 4 + (hp >> 2)) * 4096;
        e_expect(BAR(MB_OA), 14336);
        e_bulk(sb + OFF_STG0, src + 3200, 14336, BAR(MB_OA));
        e_expect(BAR(MB_OC), 32768);
        e_bulk(sb + OFF_X + 32768, src, 32768, BAR(MB_OC));
        nb_sync(NB_BDONE, 288);
        asm volatile("fence.proxy.async.shared::cta;" ::: "memory");
        e_expect(BAR(MB_OB), 18432);
        e_bulk(sb + OFF_U, src + 2048, 18432, BAR(MB_OB));
      }
    }
    return;
  }

  const int t = tid & 127;
  const int g = lane >> 2, c = lane & 3;
  {
    if (wg == 2) {
      asm volatile("setmaxnreg.inc.sync.aligned.u32 160;");
#pragma unroll
      for (int j = 0; j < 5; j++) { k[j][0] *= ksc; k[j][1] *= ksc; k[j][2] *= ksc; k[j][3] *= ksc; }
#pragma unroll 1
      for (int q = 0; q < 3; q++) {
        const uint32_t src = (q == 2 ? kp : ((tb + 127) & ~127u) + q * 2048) + lane * 16;
        const uint4 v0 = lds128(src), v1 = lds128(src + 512), v2 = lds128(src + 1024);
        const uint32_t h[10] = {v0.x, v0.y, v0.z, v0.w, v1.x, v1.y, v1.z, v1.w, v2.x, v2.y};
#pragma unroll
        for (int j = 0; j < 10; j++) {
          const float2 f = __half22float2(*(const __half2*)&h[j]);
          k[j >> 1][2 * (j & 1)] = fmaf(f.x, uf(v2.w), k[j >> 1][2 * (j & 1)]);
          k[j >> 1][2 * (j & 1) + 1] = fmaf(f.y, uf(v2.w), k[j >> 1][2 * (j & 1) + 1]);
        }
        k2048 += uf(v2.z);
      }
#pragma unroll
      for (int o2 = 4; o2; o2 >>= 1) k2048 += __shfl_xor_sync(0xffffffffu, k2048, o2);
      if (lane == 0) k[0][0] += bf_lo(dsk);
      __syncwarp();
      if (lane == 0) mbar_arrive(BAR(MB_AUX));
      TS(34);
      build_tables(tb, lane, k, k2048);
      TS(35);
      uint4* const g_y = P.xs + X_Y;
      conv_channel(sb + OFF_U + w * U_CH, tb, lane, g_y + (size_t)d * 256 + lane);
      nb_arrive(NB_BDONE, 288);
      TS(37);
      mbar_wait(BAR(MB_OA));
      const int lam = w * 8 + g;
      const uint4* src = g_y + (size_t)(oct * 32 + c * 8) * 256 + i8 * 32 + lam;
      uint4 v[8];
#pragma unroll 1
      for (int it = 0; it < SPIN_MAX; it++) {
        uint32_t m = 0xffffffffu;
#pragma unroll
        for (int i = 0; i < 8; i++) v[i] = ld_x(src + i * 256);
#pragma unroll
        for (int i = 0; i < 8; i++) m = min(m, v[i].x);
        if (__all_sync(0xffffffffu, m != 0)) break;
      }
      __nv_bfloat16* dst = P.out + (size_t)(i8 * 256 + (lam >> 2) * 16 + (lam & 3) * 2) * 1024 + 512 + oct * 32 + c * 8;
#pragma unroll
      for (int i = 0; i < 8; i++) *(uint4*)(dst + (size_t)((i >> 2) * 128 + ((i >> 1) & 1) * 8 + (i & 1)) * 1024) = tr_row(v, i);
      TS(38);
      GT(63);
      if (w == 0) TSDUMP(32);
      return;
    }
    if (wg == 1) {
      mbar_wait(BAR(MB_URAW));
      TS(48);
      uint4* dst = P.xs + X_UT + (i8 * 64 + g) * (U_CH / 16) + (c & 1) * (U_ODD / 16) + U_PAD / 16 + oct * 8 + w * 2 + (c >> 1);
      uint32_t r[8][4];
#pragma unroll
      for (int i = 0; i < 8; i++) ldsm4t(r[i], sb + OFF_STG0 + w * 4096 + lane * 128 + (((i ^ lane) & 7) << 4));
#pragma unroll
      for (int i = 0; i < 8; i++) dst[i * (U_CH / 2)] = make_uint4(r[i][0], r[i][1], r[i][2], r[i][3]);
      nb_arrive(NB_INIT, 160);
      if (lane == 0) mbar_arrive(BAR(MB_AUX));
      mbar_wait(BAR(MB_EMPTY + 4));
      mbar_spin(BAR(MB_EMPTY + 6));
    }
    TS(wg * 16 + 1);
  }

  float acc[2][48];
  {
    uint32_t fb = BAR(MB_FULL) + 64 * wg;
    uint32_t da = (uint32_t)mkdesc(sb + OFF_X, 16, 0, 0) + (wg ? 1024 : 3072), db = (uint32_t)mkdesc(sb + OFF_W, 4096, 0, 0);
    constexpr uint64_t ha = mkdesc(0, 0, 1024, 1), hb = mkdesc(0, 0, 512, 2);
#pragma unroll 1
    for (int kb = 0; kb < 8; kb++) {
      mbar_spin(fb);
      if (kb == 0) TS(wg * 16 + 2);
      WG_FENCE();
#pragma unroll
      for (int k = 0; k < 4; k++) {
        wgmma_ss_n96(acc[0], ha | (da + 2 * k), hb | (db + 64 * k), k ? 1 : kb);
        wgmma_ss_n96(acc[1], ha | (da + 2 * k + 512), hb | (db + 64 * k), k ? 1 : kb);
      }
      WG_COMMIT();
      WG_WAIT(1);
      if (kb > 0 && lane == 0) mbar_arrive(fb + 8 * (MB_EMPTY - MB_FULL - 1));
      fb += 8; db += 768;
      da = da == (uint32_t)mkdesc(sb + OFF_X + 65536, 16, 0, 0) ? da - 4096 : da + 1024;
    }
    if (wg == 0) nb_sync(NB_KREAD, 160);
    WG_WAIT(0);
    if (lane == 0) mbar_arrive(fb + 8 * (MB_EMPTY - MB_FULL - 1));
    mbar_spin(fb + 8 * (MB_EMPTY - MB_FULL - 1));
  }
  TS(wg * 16 + 3);
  asm volatile("setmaxnreg.inc.sync.aligned.u32 160;");

  constexpr uint32_t stg0 = sb + OFF_STG0, stg1 = sb + OFF_X + 32768;
  uint4* const g_part = P.xs + X_PART;
  uint4* const g_o = P.xs + X_O;
  constexpr uint32_t kvs = stg0;
  auto pack8 = [](const float* a) { return make_uint4(pack_bf(a[0], a[1]), pack_bf(a[2], a[3]), pack_bf(a[4], a[5]), pack_bf(a[6], a[7])); };
  auto feat = [&](const uint4 (&af)[4], float (&p)[4][8]) {
    WG_FENCE();
#pragma unroll
    for (int u = 0; u < 4; u++) wgmma_rs_n16(p[u], af[u], qdesc(sb + OFF_PHI + (u & 1) * 512), 0);
    WG_COMMIT();
  };
  auto exps = [&](const float (&p)[4][8], uint32_t (&e)[32]) {
#pragma unroll
    for (int u = 0; u < 4; u++) {
      const uint32_t pw[4] = {pack_bf(p[u][0], p[u][2]), pack_bf(p[u][1], p[u][3]), pack_bf(p[u][4], p[u][6]), pack_bf(p[u][5], p[u][7])};
      dual_exp(pw, e + 8 * u);
    }
  };
  auto contract = [&](float (&kc)[20], uint32_t stg, int acc_in) {
    WG_FENCE();
#pragma unroll
    for (int s = 0; s < 8; s++) wgmma_ss_n40(kc, qdesc(stg + s * SLAB), qdesc(stg + s * SLAB + 2048), s ? 1 : acc_in);
    WG_COMMIT();
    WG_WAIT(0);
  };
  uint32_t eq[32];
  float kc[20];
  {
    uint4 af[4], aq[4], vp[4];
    float p[4][8];
#pragma unroll
    for (int u = 0; u < 4; u++) af[u] = pack8(acc[u >> 1] + 16 + 8 * (u & 1));
    feat(af, p);
#pragma unroll
    for (int u = 0; u < 4; u++) { aq[u] = pack8(acc[u >> 1] + 8 * (u & 1)); vp[u] = pack8(acc[u >> 1] + 32 + 8 * (u & 1)); }
    WG_WAIT(0);
    exps(p, eq);
    TS(wg * 16 + 12);
    float rs[8][4];
    WG_FENCE();
#pragma unroll
    for (int i = 0; i < 8; i++) wgmma_rs_n8(rs[i], make_uint4(eq[4 * i], eq[4 * i + 1], eq[4 * i + 2], eq[4 * i + 3]), qdesc(sb + OFF_ONE), 0);
    WG_COMMIT();
    feat(aq, p);
    mbar_wait(BAR(MB_AUX));
    const uint32_t sl = (wg ? stg1 : stg0) + w * SLAB + lane * 16;
#pragma unroll
    for (int i = 0; i < 4; i++) stsm4(sl + (i >> 1) * 4 * SLAB + 2048 + (i & 1) * 512, vp[i].x, vp[i].y, vp[i].z, vp[i].w);
    sts128(sl + (lane >> 4) * (4 * SLAB - 256) + 3072, 0x3F803F80u, 0x3F803F80u, 0x3F803F80u, 0x3F803F80u);
    WG_WAIT(0);
#pragma unroll
    for (int i = 0; i < 8; i++) norm_store(eq + 4 * i, rs[i], sl + (i >> 2) * 4 * SLAB + (i & 3) * 512);
    asm volatile("fence.proxy.async.shared::cta;" ::: "memory");
    if (wg) {
      nb_arrive(NB_ST0, 256);
    } else {
      nb_sync(NB_WG0, 128);
      contract(kc, stg0, 0);
    }
    TS(wg * 16 + 13);
    exps(p, eq);
  }
  if (wg == 0) {
    uint4* pp = g_part + (size_t)(hp * 8 + rt) * 144 + t;
    uint32_t* pz = (uint32_t*)(pp - t + 128) + w * 16 + c * 8 + g;
    asm volatile("" : "+l"(pp), "+l"(pz));
    mbar_wait(BAR(MB_UFULL));
    TS(15);
    nb_sync(NB_ST0, 256);
    contract(kc, stg1, 1);
    TS(6);
    float kv[8];
#pragma unroll
    for (int i = 0; i < 8; i++) kv[i] = w & 2 ? kc[8 + i] : kc[i];
    st_x(pp, nz(pack_bf(kv[0], kv[1])), pack_bf(kv[2], kv[3]), pack_bf(kv[4], kv[5]), pack_bf(kv[6], kv[7]));
    if (c < 2) st_x32(pz, nz(fu(c ? kc[18] : kc[16])));
    TS(5);
  }
  TS(wg * 16 + 4);
  if (wg == 0) {
    const uint4* ps = g_part + (size_t)hp * 8 * 144 + t;
    const uint32_t* zs = (const uint32_t*)(g_part + (size_t)(hp * 8 + (lane >> 4) * 4) * 144 + 128) + w * 16 + (lane & 15);
    uint4 v[8];
    uint32_t zv[4];
#pragma unroll 1
    for (int it = 0; it < SPIN_MAX; it++) {
#pragma unroll
      for (int i = 0; i < 8; i++) v[i] = ld_x(ps + i * 144);
#pragma unroll
      for (int i = 0; i < 4; i++) zv[i] = ld_x32(zs + i * 576);
      uint32_t m = min(min(zv[0], zv[1]), min(zv[2], zv[3]));
#pragma unroll
      for (int i = 0; i < 8; i++) m = min(m, v[i].x);
      if (__all_sync(0xffffffffu, m != 0)) break;
    }
    float s[8];
    WG_FENCE();
#pragma unroll
    for (int r = 0; r < 8; r++) wgmma_rs_n16(s, v[r], qdesc(sb + OFF_EYE), r);
    WG_COMMIT();
    float zsum = (uf(zv[0]) + uf(zv[1])) + (uf(zv[2]) + uf(zv[3]));
    zsum += __shfl_xor_sync(0xffffffffu, zsum, 16);
    const uint32_t z1 = pack_bf(zsum, 1.f);
    if (lane < 16) sts128(kvs + w * 768 + 512 + lane * 16, z1, z1, z1, z1);
    WG_WAIT(0);
    stsm4(kvs + w * 768 + lane * 16, pack_bf(s[0], s[1]), pack_bf(s[2], s[3]), pack_bf(s[4], s[5]), pack_bf(s[6], s[7]));
    asm volatile("fence.proxy.async.shared::cta;" ::: "memory");
    TS(0);
  }
  nb_sync(NB_KV, 256);
  {
    float n[8][12];
    WG_FENCE();
#pragma unroll
    for (int i = 0; i < 8; i++) wgmma_rs_n24(n[i], make_uint4(eq[4 * i], eq[4 * i + 1], eq[4 * i + 2], eq[4 * i + 3]), qdesc(kvs + (i & 3) * 768), 0);
    WG_COMMIT();
    uint32_t* od = (uint32_t*)(g_o + (size_t)((rt * 4 + wg * 2) * 32 + hp * 2) * 128) + w * 64 + lane;
    WG_WAIT(0);
#pragma unroll
    for (int u = 0; u < 4; u++) {
      float(&np)[12] = n[2 * u];
      const float(&nm)[12] = n[2 * u + 1];
      const float q0 = np[9] * rcp(nm[9]), q1 = np[11] * rcp(nm[11]);
      const float r0 = rcp(fmaf(nm[8], q0, fmaf(np[9], 1e-6f, np[8]))), r1 = rcp(fmaf(nm[10], q1, fmaf(np[11], 1e-6f, np[10])));
#pragma unroll
      for (int i = 0; i < 8; i++) np[i] = fmaf(nm[i], (i & 2) ? q1 : q0, np[i]);
      uint32_t* o = od + (u >> 1) * 16384 + (u & 1) * 512;
      o[0] = pack_bf(np[0] * r0, np[1] * r0);
      o[32] = pack_bf(np[2] * r1, np[3] * r1);
      o[256] = pack_bf(np[4] * r0, np[5] * r0);
      o[288] = pack_bf(np[6] * r1, np[7] * r1);
    }
  }
  TS(wg * 16 + 7);
  nb_arrive(NB_ODONE, 320);
  if (wg) { if (w == 0) TSDUMP(16); return; }
  mbar_wait(BAR(MB_WO));
  mbar_wait(BAR(MB_OA));
  TS(8);
  nb_sync(NB_BDONE, 288);
  TS(9);
  float oc[64];
  {
    constexpr uint64_t ha = mkdesc(0, 0, 128, 0), hb = mkdesc(0, 0, 1024, 1);
    constexpr uint32_t da0 = (uint32_t)mkdesc(stg1, 1024, 0, 0), db0 = (uint32_t)mkdesc(sb + OFF_W, 8192, 0, 0);
#pragma unroll 1
    for (int j = 0; j < 8; j++) {
      const int kb = (j + 7) & 7;
      if ((j & 3) == 1) mbar_spin(j == 1 ? BAR(MB_OC) : BAR(MB_OB));
      WG_FENCE();
#pragma unroll
      for (int k = 0; k < 4; k++) wgmma_ss_n128(oc, ha | (da0 + 512 * kb + 128 * k), hb | (db0 + 1024 * kb + 128 * k), k ? 1 : j);
      WG_COMMIT();
    }
    WG_WAIT(0);
  }
  TS(10);
  nb_sync(NB_WG0, 128);
  const uint32_t ot = sb + OFF_W + w * 4096;
#pragma unroll
  for (int i = 0; i < 16; i += 2)
    stsm4(ot + (i >> 3) * 2048 + (lane & 15) * 128 + (((i + (lane >> 4)) ^ lane) & 7) * 16, pack_bf(oc[4 * i], oc[4 * i + 1]),
          pack_bf(oc[4 * i + 2], oc[4 * i + 3]), pack_bf(oc[4 * i + 4], oc[4 * i + 5]), pack_bf(oc[4 * i + 6], oc[4 * i + 7]));
  asm volatile("fence.proxy.async.shared::cta;" ::: "memory");
  __syncwarp();
  e_store3d(&mout, ot, (rt * 4 + (hp >> 2)) * 64 + w * 16, (hp & 3) * 2);
  TS(wg * 16 + 11);
  GT(61 + wg);
  if (w == 0) TSDUMP(0);
  if (w == 1) TSDUMP(48);
}

typedef CUresult (*EncodeFn)(CUtensorMap*, CUtensorMapDataType, cuuint32_t, void*, const cuuint64_t*, const cuuint64_t*,
                             const cuuint32_t*, const cuuint32_t*, CUtensorMapInterleave, CUtensorMapSwizzle,
                             CUtensorMapL2promotion, CUtensorMapFloatOOBfill);

}

extern "C" void kernel_launch(void* const* d_in, const int* in_sizes, int n_in, void* d_out, int out_size) {
  (void)in_sizes; (void)n_in; (void)out_size;
  void* fn = nullptr;
  cudaDriverEntryPointQueryResult qr;
  cudaGetDriverEntryPoint("cuTensorMapEncodeTiled", &fn, cudaEnableDefault, &qr);
  EncodeFn enc = (EncodeFn)fn;
  CUtensorMap mx, mw, mo, mu, mout, mw4;
  const cuuint32_t es[5] = {1, 1, 1, 1, 1};
  {
    cuuint64_t dims[2] = {512, 2048}, st[1] = {1024};
    cuuint32_t box[2] = {64, 128};
    enc(&mx, CU_TENSOR_MAP_DATA_TYPE_BFLOAT16, 2, d_in[0], dims, st, box, es, CU_TENSOR_MAP_INTERLEAVE_NONE,
        CU_TENSOR_MAP_SWIZZLE_128B, CU_TENSOR_MAP_L2_PROMOTION_L2_128B, CU_TENSOR_MAP_FLOAT_OOB_FILL_NONE);
  }
  {
    cuuint64_t dims[3] = {512, 512, 3}, st[2] = {3072, 1024};
    cuuint32_t box[3] = {32, 64, 3};
    enc(&mw, CU_TENSOR_MAP_DATA_TYPE_BFLOAT16, 3, d_in[1], dims, st, box, es, CU_TENSOR_MAP_INTERLEAVE_NONE,
        CU_TENSOR_MAP_SWIZZLE_64B, CU_TENSOR_MAP_L2_PROMOTION_L2_128B, CU_TENSOR_MAP_FLOAT_OOB_FILL_NONE);
  }
  {
    cuuint64_t dims[3] = {64, 512, 8}, st[2] = {1024, 128};
    cuuint32_t box[3] = {64, 64, 2};
    enc(&mo, CU_TENSOR_MAP_DATA_TYPE_BFLOAT16, 3, d_in[3], dims, st, box, es, CU_TENSOR_MAP_INTERLEAVE_NONE,
        CU_TENSOR_MAP_SWIZZLE_128B, CU_TENSOR_MAP_L2_PROMOTION_L2_128B, CU_TENSOR_MAP_FLOAT_OOB_FILL_NONE);
  }
  {
    cuuint64_t dims[5] = {512, 2, 4, 4, 64}, st[4] = {1024, 8192, 2048, 32768};
    cuuint32_t box[5] = {64, 2, 4, 4, 4};
    enc(&mu, CU_TENSOR_MAP_DATA_TYPE_BFLOAT16, 5, d_in[4], dims, st, box, es, CU_TENSOR_MAP_INTERLEAVE_NONE,
        CU_TENSOR_MAP_SWIZZLE_128B, CU_TENSOR_MAP_L2_PROMOTION_L2_128B, CU_TENSOR_MAP_FLOAT_OOB_FILL_NONE);
  }
  {
    cuuint64_t dims[3] = {64, 2048, 16}, st[2] = {2048, 128};
    cuuint32_t box[3] = {64, 16, 2};
    enc(&mout, CU_TENSOR_MAP_DATA_TYPE_BFLOAT16, 3, d_out, dims, st, box, es, CU_TENSOR_MAP_INTERLEAVE_NONE,
        CU_TENSOR_MAP_SWIZZLE_128B, CU_TENSOR_MAP_L2_PROMOTION_NONE, CU_TENSOR_MAP_FLOAT_OOB_FILL_NONE);
  }
  {
    cuuint64_t dims[4] = {512, 64, 3, 8}, st[3] = {3072, 1024, 64 * 3072};
    cuuint32_t box[4] = {32, 64, 3, 4};
    enc(&mw4, CU_TENSOR_MAP_DATA_TYPE_BFLOAT16, 4, d_in[1], dims, st, box, es, CU_TENSOR_MAP_INTERLEAVE_NONE,
        CU_TENSOR_MAP_SWIZZLE_64B, CU_TENSOR_MAP_L2_PROMOTION_L2_128B, CU_TENSOR_MAP_FLOAT_OOB_FILL_NONE);
  }
  Params P;
  P.x = (const __nv_bfloat16*)d_in[0];
  P.wphi = (const __nv_bfloat16*)d_in[2];
  P.wo = (const __nv_bfloat16*)d_in[3];
  P.logA = (const __nv_bfloat16*)d_in[5];
  P.Aim = (const __nv_bfloat16*)d_in[6];
  P.Cre = (const __nv_bfloat16*)d_in[7];
  P.Cim = (const __nv_bfloat16*)d_in[8];
  P.logdt = (const __nv_bfloat16*)d_in[9];
  P.Dskip = (const __nv_bfloat16*)d_in[10];
  P.out = (__nv_bfloat16*)d_out;
  cudaGetSymbolAddress((void**)&P.xs, g_x);
  P.ts = nullptr;
  cudaFuncSetAttribute(fused_kernel, cudaFuncAttributeMaxDynamicSharedMemorySize, SMEM_BYTES);
  fused_kernel<<<NCTA, NTHREADS, SMEM_BYTES>>>(P, mx, mw, mo, mu, mout, mw4);
}
```

```cpp
#include <cuda_runtime.h>
#include <cuda_bf16.h>
#include <cuda_fp16.h>
#include <cuda.h>
#include <stdint.h>

#define DBG_TS 0

namespace {

constexpr int NTHREADS = 512;
constexpr int NCTA = 128;
constexpr int OFF_W = 0;
constexpr int OFF_X = 98304;
constexpr int OFF_U = OFF_X + 65536;
constexpr int U_CH = 4416, U_ODD = 2240, U_PAD = 128;
constexpr int OFF_STG0 = OFF_U + 18432;
constexpr int SLAB = 3328;
constexpr int OFF_T = OFF_STG0 + 8 * SLAB;
constexpr int T_CH = 5216;
constexpr int T_D = 0;
constexpr int T_5 = 2144;
constexpr int T_3 = T_5 + 384;
constexpr int T_7 = T_5 + 1024;
constexpr int T_9 = T_7 + 320;
constexpr int T_KC = T_9 + 320;
constexpr int T_ST = T_5 - 1024;
constexpr int OFF_PHI = OFF_T + 4 * T_CH;
constexpr int OFF_EYE = OFF_PHI + 1024, OFF_ONE = OFF_EYE + 512;
constexpr int OFF_BAR = OFF_ONE + 256;
constexpr int SMEM_BYTES = OFF_BAR + 512 + 256 * DBG_TS;
constexpr uint32_t SB = 1024;
static_assert(T_KC + 2 * 656 <= T_CH, "table size");
static_assert(SMEM_BYTES <= 232448, "smem");
constexpr int MB_URAW = 0, MB_FULL = 1  , MB_WO = 17, MB_UFULL = 18, MB_OA = 19, MB_OB = 20, MB_OC = 21,
              MB_EMPTY = 22  , MB_AUX = 38;
__host__ __device__ constexpr uint32_t BAR(int i) { return SB + OFF_BAR + 8 * i; }
constexpr int NB_WG0 = 1, NB_ODONE = 2, NB_ST0 = 3  , NB_KV = 5, NB_YZ = 6, NB_INIT = 7, NB_PREP = 8, NB_PROD = 9, NB_KREAD = 10, NB_BDONE = 11, NB_ZERO = 12;
#define U_AT 2
#define ZERO_STEP 15
constexpr int SPIN_MAX = 1 << 16;

constexpr int X_CNT = 0;
constexpr int X_PART = 128;
constexpr int X_O = X_PART + 16 * 8 * 144;
constexpr int X_Y = X_O + 32 * 32 * 128;
constexpr int X_UT = X_Y + 512 * 8 * 32;
constexpr int X_SIZE = X_UT + 512 * (U_CH / 16);
__device__ __align__(128) uint4 g_x[X_SIZE];
extern __shared__ uint8_t smem_raw[];
#define TS(i) do {} while (0)
#define TS1(i) do {} while (0)
#define GT(i) do {} while (0)
#define TSDUMP(base) do {} while (0)

__device__ __forceinline__ uint32_t smem_u32(const void* p) { return (uint32_t)__cvta_generic_to_shared(p); }
__device__ __forceinline__ void mbar_arrive(uint32_t b) {
  asm volatile("mbarrier.arrive.shared::cta.b64 _, [%0];" ::"r"(b) : "memory");
}
__device__ __forceinline__ void mbar_wait(uint32_t b) {
  uint32_t done = 0;
#pragma unroll 1
  for (int i = 0; i < SPIN_MAX && !done; i++) {
    asm volatile("{\n.reg .pred p;\nmbarrier.try_wait.parity.shared::cta.b64 p, [%1], 0, 4000;\nselp.u32 %0, 1, 0, p;\n}\n"
                 : "=r"(done) : "r"(b) : "memory");
  }
}
__device__ __forceinline__ void mbar_spin(uint32_t b) {
  uint32_t done = 0;
#pragma unroll 1
  for (int i = 0; i < (SPIN_MAX << 4) && !done; i++) {
    asm volatile("{\n.reg .pred p;\nmbarrier.try_wait.parity.shared::cta.b64 p, [%1], 0;\nselp.u32 %0, 1, 0, p;\n}\n"
                 : "=r"(done) : "r"(b) : "memory");
  }
}
__device__ __forceinline__ void mbar_init(uint32_t b, int n) {
  asm volatile("mbarrier.init.shared::cta.b64 [%0], %1;" ::"r"(b), "r"(n) : "memory");
}
__device__ __forceinline__ void mbar_expect(uint32_t b, int bytes) {
  asm volatile("mbarrier.arrive.expect_tx.shared::cta.b64 _, [%0], %1;" ::"r"(b), "r"(bytes) : "memory");
}
__device__ __forceinline__ void nb_sync(int id, int n) { asm volatile("bar.sync %0, %1;" ::"r"(id), "r"(n) : "memory"); }
__device__ __forceinline__ void nb_arrive(int id, int n) { asm volatile("bar.arrive %0, %1;" ::"r"(id), "r"(n) : "memory"); }
#define ELECT "{\n.reg .pred p;\nelect.sync _|p, 0xffffffff;\n@p "
__device__ __forceinline__ void e_arrive(uint32_t b) {
  asm volatile(ELECT "mbarrier.arrive.shared::cta.b64 _, [%0];\n}\n" ::"r"(b) : "memory");
}
__device__ __forceinline__ void e_expect(uint32_t b, int bytes) {
  asm volatile(ELECT "mbarrier.arrive.expect_tx.shared::cta.b64 _, [%0], %1;\n}\n" ::"r"(b), "r"(bytes) : "memory");
}
__device__ __forceinline__ void e_tma2d(uint32_t dst, const CUtensorMap* m, uint32_t bar, int c0, int c1) {
  asm volatile(ELECT "cp.async.bulk.tensor.2d.shared::cluster.global.mbarrier::complete_tx::bytes [%0], [%1, {%3,%4}], [%2];\n}\n"
               ::"r"(dst), "l"(m), "r"(bar), "r"(c0), "r"(c1) : "memory");
}
__device__ __forceinline__ void e_tma3d(uint32_t dst, const CUtensorMap* m, uint32_t bar, int c0, int c1, int c2) {
  asm volatile(ELECT "cp.async.bulk.tensor.3d.shared::cluster.global.mbarrier::complete_tx::bytes [%0], [%1, {%3,%4,%5}], [%2];\n}\n"
               ::"r"(dst), "l"(m), "r"(bar), "r"(c0), "r"(c1), "r"(c2) : "memory");
}
__device__ __forceinline__ void e_tma4d(uint32_t dst, const CUtensorMap* m, uint32_t bar, int c0, int c3) {
  asm volatile(ELECT "cp.async.bulk.tensor.4d.shared::cluster.global.mbarrier::complete_tx::bytes [%0], [%1, {%3,%5,%5,%4}], [%2];\n}\n"
               ::"r"(dst), "l"(m), "r"(bar), "r"(c0), "r"(c3), "r"(0) : "memory");
}
__device__ __forceinline__ void e_tma5d(uint32_t dst, const CUtensorMap* m, uint32_t bar, int c0, int c4) {
  asm volatile(ELECT "cp.async.bulk.tensor.5d.shared::cluster.global.mbarrier::complete_tx::bytes [%0], [%1, {%3,%5,%5,%5,%4}], [%2];\n}\n"
               ::"r"(dst), "l"(m), "r"(bar), "r"(c0), "r"(c4), "r"(0) : "memory");
}
__device__ __forceinline__ void e_bulk(uint32_t dst, const void* src, int bytes, uint32_t bar) {
  asm volatile(ELECT "cp.async.bulk.shared::cluster.global.mbarrier::complete_tx::bytes [%0], [%1], %2, [%3];\n}\n"
               ::"r"(dst), "l"(src), "r"(bytes), "r"(bar) : "memory");
}
__device__ __forceinline__ void e_prefetch(const void* p, int bytes) {
  asm volatile(ELECT "cp.async.bulk.prefetch.L2.global [%0], %1;\n}\n" ::"l"(p), "r"(bytes) : "memory");
}
__device__ __forceinline__ void e_store3d(const CUtensorMap* m, uint32_t src, int c1, int c2) {
  asm volatile(ELECT "cp.async.bulk.tensor.3d.global.shared::cta.bulk_group [%0, {%4,%2,%3}], [%1];\n"
               "@p cp.async.bulk.commit_group;\n@p cp.async.bulk.wait_group.read 0;\n}\n"
               ::"l"(m), "r"(src), "r"(c1), "r"(c2), "r"(0) : "memory");
}
__host__ __device__ constexpr uint64_t mkdesc(uint32_t addr, uint32_t lbo, uint32_t sbo, int swz) {
  return (uint64_t)((addr & 0x3FFFF) >> 4) | ((uint64_t)(lbo >> 4) << 16) | ((uint64_t)(sbo >> 4) << 32) |
         ((uint64_t)swz << 62);
}
#define WG_FENCE() asm volatile("wgmma.fence.sync.aligned;" ::: "memory")
#define WG_COMMIT() asm volatile("wgmma.commit_group.sync.aligned;" ::: "memory")
#define WG_WAIT(n) asm volatile("wgmma.wait_group.sync.aligned " #n ";" ::: "memory")

__device__ __forceinline__ void mma(float& d0, float& d1, float& d2, float& d3, uint32_t a0, uint32_t a1, uint32_t a2,
                                    uint32_t a3, uint32_t b0, uint32_t b1) {
  asm volatile("mma.sync.aligned.m16n8k16.row.col.f32.bf16.bf16.f32 {%0,%1,%2,%3},{%4,%5,%6,%7},{%8,%9},{%0,%1,%2,%3};"
               : "+f"(d0), "+f"(d1), "+f"(d2), "+f"(d3)
               : "r"(a0), "r"(a1), "r"(a2), "r"(a3), "r"(b0), "r"(b1));
}
__device__ __forceinline__ void mmac(float (&d)[4], uint32_t a0, uint32_t a1, uint32_t a2, uint32_t a3, uint32_t b0,
                                     uint32_t b1, const float (&c)[4]) {
  asm volatile("mma.sync.aligned.m16n8k16.row.col.f32.bf16.bf16.f32 {%0,%1,%2,%3},{%4,%5,%6,%7},{%8,%9},{%10,%11,%12,%13};"
               : "=f"(d[0]), "=f"(d[1]), "=f"(d[2]), "=f"(d[3])
               : "r"(a0), "r"(a1), "r"(a2), "r"(a3), "r"(b0), "r"(b1), "f"(c[0]), "f"(c[1]), "f"(c[2]), "f"(c[3]));
}
__device__ __forceinline__ void mma_p(int p, float (&d)[4], uint32_t a0, uint32_t a1, uint32_t a2, uint32_t a3, uint32_t b0, uint32_t b1) {
  asm volatile("{\n.reg .pred q;\nsetp.ne.b32 q, %10, 0;\n"
               "@q mma.sync.aligned.m16n8k16.row.col.f32.bf16.bf16.f32 {%0,%1,%2,%3},{%4,%5,%6,%7},{%8,%9},{%0,%1,%2,%3};\n}\n"
               : "+f"(d[0]), "+f"(d[1]), "+f"(d[2]), "+f"(d[3])
               : "r"(a0), "r"(a1), "r"(a2), "r"(a3), "r"(b0), "r"(b1), "r"(p));
}
__device__ __forceinline__ void mmac_p(int p, float (&d)[4], uint32_t a0, uint32_t a1, uint32_t a2, uint32_t a3, uint32_t b0,
                                       uint32_t b1, const float (&c)[4]) {
  asm volatile("{\n.reg .pred q;\nsetp.ne.b32 q, %14, 0;\n"
               "@q mma.sync.aligned.m16n8k16.row.col.f32.bf16.bf16.f32 {%0,%1,%2,%3},{%4,%5,%6,%7},{%8,%9},{%10,%11,%12,%13};\n}\n"
               : "+f"(d[0]), "+f"(d[1]), "+f"(d[2]), "+f"(d[3])
               : "r"(a0), "r"(a1), "r"(a2), "r"(a3), "r"(b0), "r"(b1), "f"(c[0]), "f"(c[1]), "f"(c[2]), "f"(c[3]), "r"(p));
}
__device__ __forceinline__ void mma_h(float (&d)[4], const uint32_t (&a)[4], uint32_t b0, uint32_t b1) {
  asm volatile("mma.sync.aligned.m16n8k16.row.col.f32.f16.f16.f32 {%0,%1,%2,%3},{%4,%5,%6,%7},{%8,%9},{%0,%1,%2,%3};"
               : "+f"(d[0]), "+f"(d[1]), "+f"(d[2]), "+f"(d[3]) : "r"(a[0]), "r"(a[1]), "r"(a[2]), "r"(a[3]), "r"(b0), "r"(b1));
}
__device__ __forceinline__ void mma0(float& d0, float& d1, float& d2, float& d3, uint32_t a0, uint32_t a1, uint32_t a2,
                                     uint32_t a3, uint32_t b0, uint32_t b1) {
  asm volatile("mma.sync.aligned.m16n8k16.row.col.f32.bf16.bf16.f32 {%0,%1,%2,%3},{%4,%5,%6,%7},{%8,%9},{%10,%10,%10,%10};"
               : "=f"(d0), "=f"(d1), "=f"(d2), "=f"(d3)
               : "r"(a0), "r"(a1), "r"(a2), "r"(a3), "r"(b0), "r"(b1), "f"(0.f));
}
__device__ __forceinline__ uint32_t pack_bf(float lo, float hi) {
  uint32_t r;
  asm("cvt.rn.bf16x2.f32 %0, %1, %2;" : "=r"(r) : "f"(hi), "f"(lo));
  return r;
}
__device__ __forceinline__ float bf_lo(uint32_t w) { return __uint_as_float(w << 16); }
__device__ __forceinline__ float bf_hi(uint32_t w) { return __uint_as_float(w & 0xffff0000u); }
__device__ __forceinline__ float bf_round(float x) { return __bfloat162float(__float2bfloat16_rn(x)); }
__device__ __forceinline__ uint32_t bmax2(uint32_t a, uint32_t b) {
  uint32_t r; asm("max.bf16x2 %0, %1, %2;" : "=r"(r) : "r"(a), "r"(b)); return r;
}
__device__ __forceinline__ uint32_t bmin2(uint32_t a, uint32_t b) {
  uint32_t r; asm("min.bf16x2 %0, %1, %2;" : "=r"(r) : "r"(a), "r"(b)); return r;
}
__device__ __forceinline__ float ex2(float x) { float r; asm("ex2.approx.ftz.f32 %0, %1;" : "=f"(r) : "f"(x)); return r; }
__device__ __forceinline__ float rcp(float x) { float r; asm("rcp.approx.ftz.f32 %0, %1;" : "=f"(r) : "f"(x)); return r; }
__device__ __forceinline__ void ldsm4(uint32_t (&r)[4], uint32_t a) {
  asm volatile("ldmatrix.sync.aligned.m8n8.x4.shared.b16 {%0,%1,%2,%3}, [%4];"
               : "=r"(r[0]), "=r"(r[1]), "=r"(r[2]), "=r"(r[3]) : "r"(a) : "memory");
}
__device__ __forceinline__ void ldsm4t(uint32_t (&r)[4], uint32_t a) {
  asm volatile("ldmatrix.sync.aligned.m8n8.x4.trans.shared.b16 {%0,%1,%2,%3}, [%4];"
               : "=r"(r[0]), "=r"(r[1]), "=r"(r[2]), "=r"(r[3]) : "r"(a) : "memory");
}
__device__ __forceinline__ void stsm4(uint32_t a, uint32_t r0, uint32_t r1, uint32_t r2, uint32_t r3) {
  asm volatile("stmatrix.sync.aligned.m8n8.x4.shared.b16 [%0], {%1,%2,%3,%4};"
               ::"r"(a), "r"(r0), "r"(r1), "r"(r2), "r"(r3) : "memory");
}
__device__ __forceinline__ uint32_t lds32(uint32_t a) {
  uint32_t r; asm volatile("ld.shared.u32 %0, [%1];" : "=r"(r) : "r"(a) : "memory"); return r;
}
__device__ __forceinline__ uint32_t lds16(uint32_t a) {
  uint32_t r; asm volatile("{\n.reg .u16 h;\nld.shared.u16 h, [%1];\ncvt.u32.u16 %0, h;\n}\n" : "=r"(r) : "r"(a) : "memory"); return r;
}
__device__ __forceinline__ uint2 lds64(uint32_t a) {
  uint2 r; asm volatile("ld.shared.v2.u32 {%0,%1}, [%2];" : "=r"(r.x), "=r"(r.y) : "r"(a) : "memory"); return r;
}
__device__ __forceinline__ uint4 lds128(uint32_t a) {
  uint4 r;
  asm volatile("ld.shared.v4.u32 {%0,%1,%2,%3}, [%4];" : "=r"(r.x), "=r"(r.y), "=r"(r.z), "=r"(r.w) : "r"(a) : "memory");
  return r;
}
__device__ __forceinline__ void sts32(uint32_t a, uint32_t v) { asm volatile("st.shared.u32 [%0], %1;" ::"r"(a), "r"(v) : "memory"); }
__device__ __forceinline__ void sts16(uint32_t a, uint32_t v) {
  asm volatile("{\n.reg .u16 h;\ncvt.u16.u32 h, %1;\nst.shared.u16 [%0], h;\n}\n" ::"r"(a), "r"(v) : "memory");
}
__device__ __forceinline__ void sts64(uint32_t a, uint32_t x, uint32_t y) {
  asm volatile("st.shared.v2.u32 [%0], {%1,%2};" ::"r"(a), "r"(x), "r"(y) : "memory");
}
__device__ __forceinline__ void sts128(uint32_t a, uint32_t x, uint32_t y, uint32_t z, uint32_t w) {
  asm volatile("st.shared.v4.u32 [%0], {%1,%2,%3,%4};" ::"r"(a), "r"(x), "r"(y), "r"(z), "r"(w) : "memory");
}
__device__ __forceinline__ uint4 ld_x(const uint4* p) {
  uint4 r;
  asm volatile("{\n.reg .b128 t;\nld.relaxed.gpu.global.b128 t, [%4];\nmov.b128 {%0,%1,%2,%3}, t;\n}\n"
               : "=r"(r.x), "=r"(r.y), "=r"(r.z), "=r"(r.w) : "l"(p) : "memory");
  return r;
}
__device__ __forceinline__ uint32_t ld_x32(const uint32_t* p) {
  uint32_t r; asm volatile("ld.relaxed.gpu.global.u32 %0, [%1];" : "=r"(r) : "l"(p) : "memory"); return r;
}
__device__ __forceinline__ void st_x(uint4* p, uint32_t x, uint32_t y, uint32_t z, uint32_t w) {
  asm volatile("{\n.reg .b128 t;\nmov.b128 t, {%1,%2,%3,%4};\nst.relaxed.gpu.global.b128 [%0], t;\n}\n"
               ::"l"(p), "r"(x), "r"(y), "r"(z), "r"(w) : "memory");
}
__device__ __forceinline__ void st_x_p(int p, uint4* a, uint32_t x, uint32_t y, uint32_t z, uint32_t w) {
  asm volatile("{\n.reg .b128 t;\n.reg .pred q;\nsetp.ne.b32 q, %5, 0;\nmov.b128 t, {%1,%2,%3,%4};\n@q st.relaxed.gpu.global.b128 [%0], t;\n}\n"
               ::"l"(a), "r"(x), "r"(y), "r"(z), "r"(w), "r"(p) : "memory");
}
__device__ __forceinline__ void sts64_p(int p, uint32_t a, uint32_t x, uint32_t y) {
  asm volatile("{\n.reg .pred q;\nsetp.ne.b32 q, %3, 0;\n@q st.shared.v2.u32 [%0], {%1,%2};\n}\n" ::"r"(a), "r"(x), "r"(y), "r"(p) : "memory");
}
__device__ __forceinline__ void st_x32(uint32_t* p, uint32_t x) {
  asm volatile("st.relaxed.gpu.global.u32 [%0], %1;" ::"l"(p), "r"(x) : "memory");
}
__device__ __forceinline__ uint32_t nz(uint32_t w) { return max(w, 1u); }
__device__ __forceinline__ uint32_t fu(float x) { return __float_as_uint(x); }
__device__ __forceinline__ float uf(uint32_t x) { return __uint_as_float(x); }

__device__ __forceinline__ void wgmma_ss_n96(float (&d)[48], uint64_t da, uint64_t db, int sc) {
  asm volatile("{\n.reg .pred p;\nsetp.ne.b32 p, %50, 0;\n"
      "wgmma.mma_async.sync.aligned.m64n96k16.f32.bf16.bf16 "
      "{%0,%1,%2,%3,%4,%5,%6,%7,%8,%9,%10,%11,%12,%13,%14,%15,%16,%17,%18,%19,%20,%21,%22,%23,%24,%25,%26,%27,%28,%29,%30,%31,%32,%33,%34,%35,%36,%37,%38,%39,%40,%41,%42,%43,%44,%45,%46,%47}, "
      "%48, %49, p, 1, 1, 0, 1;\n}\n"
      : "+f"(d[0]), "+f"(d[1]), "+f"(d[2]), "+f"(d[3]), "+f"(d[4]), "+f"(d[5]), "+f"(d[6]), "+f"(d[7]),
        "+f"(d[8]), "+f"(d[9]), "+f"(d[10]), "+f"(d[11]), "+f"(d[12]), "+f"(d[13]), "+f"(d[14]), "+f"(d[15]),
        "+f"(d[16]), "+f"(d[17]), "+f"(d[18]), "+f"(d[19]), "+f"(d[20]), "+f"(d[21]), "+f"(d[22]), "+f"(d[23]),
        "+f"(d[24]), "+f"(d[25]), "+f"(d[26]), "+f"(d[27]), "+f"(d[28]), "+f"(d[29]), "+f"(d[30]), "+f"(d[31]),
        "+f"(d[32]), "+f"(d[33]), "+f"(d[34]), "+f"(d[35]), "+f"(d[36]), "+f"(d[37]), "+f"(d[38]), "+f"(d[39]),
        "+f"(d[40]), "+f"(d[41]), "+f"(d[42]), "+f"(d[43]), "+f"(d[44]), "+f"(d[45]), "+f"(d[46]), "+f"(d[47])
      : "l"(da), "l"(db), "r"(sc));
}

__device__ __forceinline__ void wgmma_ss_n128(float (&d)[64], uint64_t da, uint64_t db, int sc) {
  asm volatile("{\n.reg .pred p;\nsetp.ne.b32 p, %66, 0;\n"
      "wgmma.mma_async.sync.aligned.m64n128k16.f32.bf16.bf16 "
      "{%0,%1,%2,%3,%4,%5,%6,%7,%8,%9,%10,%11,%12,%13,%14,%15,%16,%17,%18,%19,%20,%21,%22,%23,%24,%25,%26,%27,%28,%29,%30,%31,%32,%33,%34,%35,%36,%37,%38,%39,%40,%41,%42,%43,%44,%45,%46,%47,%48,%49,%50,%51,%52,%53,%54,%55,%56,%57,%58,%59,%60,%61,%62,%63}, "
      "%64, %65, p, 1, 1, 0, 1;\n}\n"
      : "+f"(d[0]), "+f"(d[1]), "+f"(d[2]), "+f"(d[3]), "+f"(d[4]), "+f"(d[5]), "+f"(d[6]), "+f"(d[7]),
        "+f"(d[8]), "+f"(d[9]), "+f"(d[10]), "+f"(d[11]), "+f"(d[12]), "+f"(d[13]), "+f"(d[14]), "+f"(d[15]),
        "+f"(d[16]), "+f"(d[17]), "+f"(d[18]), "+f"(d[19]), "+f"(d[20]), "+f"(d[21]), "+f"(d[22]), "+f"(d[23]),
        "+f"(d[24]), "+f"(d[25]), "+f"(d[26]), "+f"(d[27]), "+f"(d[28]), "+f"(d[29]), "+f"(d[30]), "+f"(d[31]),
        "+f"(d[32]), "+f"(d[33]), "+f"(d[34]), "+f"(d[35]), "+f"(d[36]), "+f"(d[37]), "+f"(d[38]), "+f"(d[39]),
        "+f"(d[40]), "+f"(d[41]), "+f"(d[42]), "+f"(d[43]), "+f"(d[44]), "+f"(d[45]), "+f"(d[46]), "+f"(d[47]),
        "+f"(d[48]), "+f"(d[49]), "+f"(d[50]), "+f"(d[51]), "+f"(d[52]), "+f"(d[53]), "+f"(d[54]), "+f"(d[55]),
        "+f"(d[56]), "+f"(d[57]), "+f"(d[58]), "+f"(d[59]), "+f"(d[60]), "+f"(d[61]), "+f"(d[62]), "+f"(d[63])
      : "l"(da), "l"(db), "r"(sc));
}

__device__ __forceinline__ void wgmma_ss_n40(float (&d)[20], uint64_t da, uint64_t db, int sc) {
  asm volatile("{\n.reg .pred p;\nsetp.ne.b32 p, %22, 0;\n"
      "wgmma.mma_async.sync.aligned.m64n40k16.f32.bf16.bf16 "
      "{%0,%1,%2,%3,%4,%5,%6,%7,%8,%9,%10,%11,%12,%13,%14,%15,%16,%17,%18,%19}, "
      "%20, %21, p, 1, 1, 1, 1;\n}\n"
      : "+f"(d[0]), "+f"(d[1]), "+f"(d[2]), "+f"(d[3]), "+f"(d[4]), "+f"(d[5]), "+f"(d[6]), "+f"(d[7]),
        "+f"(d[8]), "+f"(d[9]), "+f"(d[10]), "+f"(d[11]), "+f"(d[12]), "+f"(d[13]), "+f"(d[14]), "+f"(d[15]),
        "+f"(d[16]), "+f"(d[17]), "+f"(d[18]), "+f"(d[19])
      : "l"(da), "l"(db), "r"(sc));
}

__device__ __forceinline__ void wgmma_rs_n8(float (&d)[4], const uint4& a, uint64_t db, int sc) {
  asm volatile("{\n.reg .pred p;\nsetp.ne.b32 p, %9, 0;\n"
      "wgmma.mma_async.sync.aligned.m64n8k16.f32.bf16.bf16 "
      "{%0,%1,%2,%3}, "
      "{%4,%5,%6,%7}, %8, p, 1, 1, 1;\n}\n"
      : "+f"(d[0]), "+f"(d[1]), "+f"(d[2]), "+f"(d[3])
      : "r"(a.x), "r"(a.y), "r"(a.z), "r"(a.w), "l"(db), "r"(sc));
}

__device__ __forceinline__ void wgmma_rs_n16(float (&d)[8], const uint4& a, uint64_t db, int sc) {
  asm volatile("{\n.reg .pred p;\nsetp.ne.b32 p, %13, 0;\n"
      "wgmma.mma_async.sync.aligned.m64n16k16.f32.bf16.bf16 "
      "{%0,%1,%2,%3,%4,%5,%6,%7}, "
      "{%8,%9,%10,%11}, %12, p, 1, 1, 1;\n}\n"
      : "+f"(d[0]), "+f"(d[1]), "+f"(d[2]), "+f"(d[3]), "+f"(d[4]), "+f"(d[5]), "+f"(d[6]), "+f"(d[7])
      : "r"(a.x), "r"(a.y), "r"(a.z), "r"(a.w), "l"(db), "r"(sc));
}

__device__ __forceinline__ void wgmma_rs_n24(float (&d)[12], const uint4& a, uint64_t db, int sc) {
  asm volatile("{\n.reg .pred p;\nsetp.ne.b32 p, %17, 0;\n"
      "wgmma.mma_async.sync.aligned.m64n24k16.f32.bf16.bf16 "
      "{%0,%1,%2,%3,%4,%5,%6,%7,%8,%9,%10,%11}, "
      "{%12,%13,%14,%15}, %16, p, 1, 1, 1;\n}\n"
      : "+f"(d[0]), "+f"(d[1]), "+f"(d[2]), "+f"(d[3]), "+f"(d[4]), "+f"(d[5]), "+f"(d[6]), "+f"(d[7]),
        "+f"(d[8]), "+f"(d[9]), "+f"(d[10]), "+f"(d[11])
      : "r"(a.x), "r"(a.y), "r"(a.z), "r"(a.w), "l"(db), "r"(sc));
}

struct Params {
  const __nv_bfloat16 *logA, *Aim, *Cre, *Cim, *logdt, *Dskip, *x, *wphi, *wo;
  __nv_bfloat16* out;
  uint4* xs;
  long long* ts;
};

__device__ __forceinline__ uint4 tr_row(const uint4 (&v)[8], int i) {
  uint32_t o[4];
#pragma unroll
  for (int m = 0; m < 4; m++) {
    const uint4 &ra = v[2 * m], &rb = v[2 * m + 1];
    const int k = i >> 1;
    const uint32_t xa = k == 0 ? ra.x : k == 1 ? ra.y : k == 2 ? ra.z : ra.w;
    const uint32_t xb = k == 0 ? rb.x : k == 1 ? rb.y : k == 2 ? rb.z : rb.w;
    o[m] = __byte_perm(xa, xb, (i & 1) ? 0x7632 : 0x5410);
  }
  return make_uint4(o[0], o[1], o[2], o[3]);
}

struct cpx { float r, i; };
__device__ __forceinline__ cpx csq(cpx a) { return {a.r * a.r - a.i * a.i, 2.f * (a.r * a.i)}; }
__device__ __forceinline__ cpx polar(float e, float t) {
  const float m = ex2(e);
  return {m * __cosf(t), m * __sinf(t)};
}

struct KgenRaw { unsigned short la, ai, cr, ci, ldt; };
__device__ __forceinline__ KgenRaw kgen_load(const Params& P, int d, int unit, int lane) {
  const int o = d * 128 + unit * 32 + lane;
  return {__ldg((const unsigned short*)P.logA + o), __ldg((const unsigned short*)P.Aim + o), __ldg((const unsigned short*)P.Cre + o),
          __ldg((const unsigned short*)P.Cim + o), __ldg((const unsigned short*)P.logdt + d)};
}
struct hmul { __half2 a, b; };
__device__ __forceinline__ hmul mk_mul(cpx w) {
  uint32_t b;
  asm("{\n.reg .f32 n;\nneg.ftz.f32 n, %1;\ncvt.rn.f16x2.f32 %0, %2, n;\n}\n" : "=r"(b) : "f"(w.i), "f"(w.r));
  return {__floats2half2_rn(w.r, w.i), *(const __half2*)&b};
}
__device__ __forceinline__ __half2 hcm(__half2 z, const hmul& w) { return __hfma2(__high2half2(z), w.b, __hmul2(__low2half2(z), w.a)); }
__device__ __forceinline__ uint32_t hu(__half2 v) { return *(const uint32_t*)&v; }

struct KgenAddr { uint32_t sa, sb, lb, lc, la; };
__device__ __forceinline__ KgenAddr kgen_addr(int lane, uint32_t buf) {
  KgenAddr a;
  a.sa = buf + (lane & 7) * 128 + ((((lane >> 3) ^ lane) & 7) << 4);
  a.lb = buf + (lane >> 3) * 128 + (((lane ^ (lane >> 3)) & 7) << 4);
  a.la = buf + ((lane >> 3) & 1) * 1024 + (lane >> 4) * 128 + (((lane ^ (lane >> 4)) & 7) << 4);
  a.sb = a.sa ^ 64; a.lc = a.lb ^ 64;
  asm volatile("" : "+r"(a.sa), "+r"(a.sb), "+r"(a.lb), "+r"(a.lc), "+r"(a.la));
  return a;
}
__device__ __forceinline__ void kgen_unit(const KgenRaw& r, const KgenAddr& ad, uint32_t zero, float (&k)[5][4], float& k2048, float& sc) {
  const float dt = bf_round(expf(bf_lo(r.ldt)));
  const float a2 = bf_round(ex2(bf_lo(r.la) * 1.4426950408889634f)) * (dt * -1.4426950408889634f);
  const float f = bf_lo(r.ai) * dt;
  const float r128 = f * 20.371832715762604f;
  const uint32_t ex = min(max(__reduce_max_sync(0xffffffffu, max(r.cr & 0x7fffu, r.ci & 0x7fffu)) >> 7, 1u), 253u);
  const float cs = uf((254u - ex) << 23);
  sc = 2.f * dt * uf(ex << 23);
  const cpx C = {bf_lo(r.cr) * cs, -bf_lo(r.ci) * cs};
  auto put = [&](const __half2 (&v)[8], uint32_t off) {
    stsm4(ad.sa + off, hu(v[0]), hu(v[1]), hu(v[2]), hu(v[3]));
    stsm4(ad.sb + off, hu(v[4]), hu(v[5]), hu(v[6]), hu(v[7]));
  };
  uint32_t A[4][4], B[5][2][4];
  auto get = [&](int j, uint32_t off) {
    __syncwarp();
    ldsm4(B[j][0], ad.lb + off);
    ldsm4(B[j][1], ad.lc + 512 + off);
  };
  auto tile = [&](int j) {
    k[j][0] = k[j][1] = k[j][2] = k[j][3] = 0.f;
#pragma unroll
    for (int s = 0; s < 4; s++) mma_h(k[j], A[s], B[j][s >> 1][2 * (s & 1)], B[j][s >> 1][2 * (s & 1) + 1]);
  };
  auto after = [&](cpx v, uint32_t dep) { return cpx{uf(fu(v.r) ^ (dep & zero)), v.i}; };
  const cpx w1 = polar(a2, f), w128 = polar(a2 * 128.f, (r128 - rintf(r128)) * 6.283185307179586f);
  const cpx w2 = csq(w1), w4 = csq(w2);
  __half2 t0[8], t1[8], t2[8], t3[8], t4[8];
  const hmul m2 = mk_mul(w2), m4 = mk_mul(w4), m128 = mk_mul(w128);
  t0[0] = __floats2half2_rn(1.f, 0.f); t0[1] = __floats2half2_rn(w1.r, w1.i); t0[2] = m2.a; t0[4] = m4.a;
  t0[3] = hcm(t0[1], m2); t0[5] = hcm(t0[1], m4); t0[6] = hcm(t0[2], m4); t0[7] = hcm(t0[3], m4);
  put(t0, 0); get(0, 0);
  t1[0] = m128.a;
#pragma unroll
  for (int i = 1; i < 8; i++) t1[i] = hcm(t0[i], m128);
  put(t1, 1024); get(1, 1024);
  {
    cpx w8 = csq(after(w4, B[0][0][0]));
    w8.i = -w8.i;
    const cpx w16 = csq(w8), w32 = csq(w16), w64 = csq(w32);
    const hmul m8 = mk_mul(w8), m16 = mk_mul(w16), m32 = mk_mul(w32), m64 = mk_mul(w64);
    __half2 a[8];
    a[0] = __floats2half2_rn(C.r, C.i); a[1] = hcm(a[0], m8);
    a[2] = hcm(a[0], m16); a[3] = hcm(a[1], m16);
#pragma unroll
    for (int i = 0; i < 4; i++) a[4 + i] = hcm(a[i], m32);
    put(a, 0);
#pragma unroll
    for (int i = 0; i < 8; i++) a[i] = hcm(a[i], m64);
    put(a, 1024);
    __syncwarp();
#pragma unroll
    for (int s = 0; s < 4; s++) ldsm4(A[s], (ad.la ^ (s << 5)) + s * 256);
  }
  const cpx w256 = csq(after(w128, B[1][0][0]));
  const hmul m256 = mk_mul(w256);
  t2[0] = m256.a;
#pragma unroll
  for (int i = 1; i < 8; i++) t2[i] = hcm((i & 1) ? t1[i & 6] : t0[i & 6], m256);
  put(t2, 0); get(2, 0);
  tile(0); tile(1);
  const cpx w512 = csq(after(w256, A[0][0]));
  const hmul m512 = mk_mul(w512);
  t3[0] = m512.a;
#pragma unroll
  for (int i = 1; i < 8; i++) t3[i] = hcm((i & 2) ? t2[i & 5] : ((i & 1) ? t1[i & 4] : t0[i & 4]), m512);
  put(t3, 1024); get(3, 1024);
  tile(2);
  const cpx w1024 = csq(after(w512, B[2][0][0])), we = csq(w1024);
  const hmul m1024 = mk_mul(w1024);
  t4[0] = m1024.a;
#pragma unroll
  for (int i = 1; i < 8; i++) t4[i] = hcm((i & 4) ? t3[i & 3] : ((i & 2) ? t2[i & 1] : t1[0]), m1024);
  put(t4, 0); get(4, 0);
  tile(3); tile(4);
  k2048 = (C.r * we.r + C.i * we.i) * sc;
}

__device__ __forceinline__ void build_tables(uint32_t tb, int lane, float (&k)[5][4], float k2048) {
  const int g = lane >> 2, c = lane & 3;
  const uint32_t kc = tb + T_KC + 16;
  {
    const uint32_t a0 = kc + 16 * g + 4 * c, a2 = kc + 2 * (256 + 4 * g + c);
    const uint32_t a3 = kc + 2 * (384 + 2 * g + 64 * (c & 1) + (c >> 1)), a4 = kc + 2 * (512 + g + 32 * c);
#pragma unroll
    for (int r = 0; r < 2; r++) {
      sts32(a0 + 128 * r, pack_bf(k[0][2 * r], k[0][2 * r + 1]));
      sts32(a0 + 128 * r + 256, pack_bf(k[1][2 * r], k[1][2 * r + 1]));
      const uint32_t w2 = pack_bf(k[2][2 * r], k[2][2 * r + 1]);
      const uint32_t w3 = pack_bf(k[3][2 * r], k[3][2 * r + 1]);
      const uint32_t w4 = pack_bf(k[4][2 * r], k[4][2 * r + 1]);
      sts16(a2 + 64 * r, w2); sts16(a2 + 64 * r + 128, w2 >> 16);
      sts16(a3 + 32 * r, w3); sts16(a3 + 32 * r + 64, w3 >> 16);
      sts16(a4 + 16 * r, w4); sts16(a4 + 16 * r + 32, w4 >> 16);
    }
  }
  if (lane == 0) { sts16(kc + 2 * 640, pack_bf(k2048, 0.f)); sts16(kc - 2, 0); }
  __syncwarp();
  const uint32_t td = tb + T_D + 32;
  {
    const uint4 v = lds128(kc + 16 * lane);
    const uint32_t pv = lds16(kc + 16 * lane - 2);
    sts128(td + 32 * lane, __byte_perm(v.x, pv, 0x5410), __byte_perm(v.x, v.x, 0x1032), __byte_perm(v.y, v.x, 0x7610),
           __byte_perm(v.y, v.y, 0x1032));
    sts128(td + 32 * lane + 16, __byte_perm(v.z, v.y, 0x7610), __byte_perm(v.z, v.z, 0x1032),
           __byte_perm(v.w, v.z, 0x7610), __byte_perm(v.w, v.w, 0x1032));
  }
  {
    const uint2 v = lds64(kc + 512 + 8 * lane);
    const uint32_t k4 = lds16(kc + 512 + 8 * lane + 8);
    const uint32_t pv = lds16(kc + (lane == 0 ? 510 : 512 + 8 * lane));
    const uint32_t k22 = __byte_perm(v.y, v.y, 0x1010);
    sts128(td + 1024 + 32 * lane, __byte_perm(v.x, pv, 0x5410), __byte_perm(v.x, v.x, 0x1010),
           __byte_perm(v.x, v.x, 0x1032), __byte_perm(v.y, v.x, 0x7610));
    sts128(td + 1024 + 32 * lane + 16, k22, k22, __byte_perm(v.y, v.y, 0x1032), __byte_perm(k4, v.y, 0x7610));
  }
  {
    const uint32_t kk = lds16(kc + 2 * 384);
    const uint32_t w = lane < 3 ? (kk | (kk << 16)) : (lane == 3 ? (kk << 16) : 0u);
    if (lane < 24) sts32(td + 4 * (lane < 16 ? 512 + lane : lane - 24), w);
    const uint32_t lo_ = lds16(kc + 2 * 511), le_ = lds16(kc + 2 * 512);
    const uint32_t ja = tb + T_5 + (lane < 16 ? 4 * lane : 256 + 4 * lane);
    sts32(ja, lane == 16 ? (le_ << 16) : 0u);
    sts32(ja + 384, lane == 16 ? (lo_ << 16) : 0u);
    sts32(tb + (lane < 16 ? T_7 : T_9 - 64) + 4 * lane, 0u);
  }
#pragma unroll
  for (int s = 0; s < 2; s++) {
    const uint32_t b = kc + 2 * (s ? 512 : 384) + 8 * lane;
    const uint2 v = lds64(b);
    uint32_t em = lds16(b - 2), e0 = v.x;
    const uint32_t e4 = lds16(b + 8);
    if (lane == 0) { em = 0; e0 = 0; }
    sts64(tb + (s ? T_7 : T_3) + 64 + 8 * lane, __byte_perm(v.x, em, 0x5432), __byte_perm(v.y, v.x, 0x7632));
    sts64(tb + (s ? T_9 : T_5) + 64 + 8 * lane, __byte_perm(v.y, e0, 0x5410), __byte_perm(e4, v.y, 0x5410));
  }
  __syncwarp();
}

__device__ __forceinline__ uint32_t box2w(int lo, int n, int o) {
  return ((unsigned)(o - lo) < (unsigned)n ? 0x3F80u : 0u) | ((unsigned)(o + 1 - lo) < (unsigned)n ? 0x3F800000u : 0u);
}

#define SPLIT() asm volatile("{\n.reg .pred p;\nsetp.ne.u32 p, %0, 0;\n@p exit;\n}\n" ::"r"(blockIdx.y) : "memory")

__device__ __forceinline__ void conv_channel(uint32_t ub, uint32_t tb, int lane, uint4* ydst) {
  const int g = lane >> 2, c = lane & 3, x = g - 2 * c;
  const int mi = lane >> 3;
  const uint32_t qa = ub + U_PAD + 16 * (lane & 7) + ((mi == 0 || mi == 3) ? U_ODD : 0) - (mi == 0 ? 16 : 0);
  const uint32_t hb = ub + U_PAD + (mi & 1) * U_ODD + 16 * ((lane >> 4) + (lane & 7)) - 16;
  const uint32_t kv = lds16(tb + T_KC + 16 + 2 * 512);
  const int oh = c < 2 ? 8 + 2 * c : 2 * c - 8, og = c < 3 ? 2 * c : -10;
  uint32_t bx[4] = {box2w(g - 4, 9, 2 * c), box2w(g - 3, 7, 2 * c), box2w(g - 4, 9, oh), box2w(g - 3, 7, oh)};
  uint32_t by[4] = {box2w(g - 10, 5, 2 * c - 8), box2w(g - 5, 3, 2 * c - 8), box2w(g - 10, 5, og), box2w(g - 5, 3, og)};
  uint32_t lb0 = ((unsigned)(x + 5) < 2u ? kv : 0u) | ((unsigned)(x + 4) < 2u ? kv << 16 : 0u);
  uint32_t lb1 = ((unsigned)(x - 3) < 2u ? kv : 0u) | ((unsigned)(x - 4) < 2u ? kv << 16 : 0u);
  const int q0 = g - 1, q1 = c < 3 ? g : g - 2;
  uint32_t y0a = ub + U_PAD + (q0 & 1) * U_ODD + 16 * (q0 >> 1) + 4 * c;
  uint32_t y1a = ub + U_PAD + (q1 & 1) * U_ODD + 16 * (q1 >> 1) + 4 * c;
  uint32_t f3[3][4][4];
  {
    const uint32_t fa = tb + T_7 + 4 * (16 + x);
#pragma unroll
    for (int tt = 0; tt < 3; tt++)
#pragma unroll
      for (int D = 0; D < 4; D++) {
        const uint32_t a = fa + (tt == 0 ? 316 : (tt == 1 ? 320 : 0)) + 64 * D;
        f3[tt][D][0] = lds32(a); f3[tt][D][1] = lds32(a + 32); f3[tt][D][2] = lds32(a - 32); f3[tt][D][3] = lds32(a);
      }
  }
#pragma unroll
  for (int i = 0; i < 4; i++) asm volatile("" : "+r"(bx[i]), "+r"(by[i]));
  asm volatile("" : "+r"(lb0), "+r"(lb1), "+r"(y0a), "+r"(y1a));
  mbar_wait(BAR(MB_UFULL));
  mbar_wait(BAR(MB_EMPTY + 15));
  TS(36);
  float acc[16][4];
  {
    uint32_t z09[8], z07[8], zm9[8], zm7[8];
#pragma unroll
    for (int i = 0; i < 8; i++) {
      uint32_t h[4];
      ldsm4(h, hb + 128 * i);
      float y0, y1, y2, y3, w0, w1, w2, w3;
      mma0(y0, y1, y2, y3, bx[0], bx[1], bx[2], bx[3], h[2], c < 2 ? h[3] : h[1]);
      mma0(w0, w1, w2, w3, bx[0], bx[1], bx[2], bx[3], h[1], c < 2 ? h[2] : h[0]);
      z09[i] = pack_bf(y0, y1); z07[i] = pack_bf(y2, y3);
      zm9[i] = pack_bf(w0, w1); zm7[i] = pack_bf(w2, w3);
    }
    float a[4][2][4];
#pragma unroll
    for (int kap = 0; kap < 4; kap++)
#pragma unroll
      for (int sg = 0; sg < 2; sg++)
#pragma unroll
        for (int bk = 3; bk >= kap; bk--) {
          const uint32_t(&q0_)[4] = f3[sg ? 2 : 0][bk - kap];
          const uint32_t(&q1_)[4] = f3[sg ? 2 : 1][bk - kap];
          float(&a0)[4] = a[bk][0];
          float(&a1)[4] = a[bk][1];
          if (sg == 0 && kap == 0) {
            mma0(a0[0], a0[1], a0[2], a0[3], q0_[0], q0_[1], q0_[2], q0_[3], z09[0], z09[1]);
            mma0(a1[0], a1[1], a1[2], a1[3], q1_[0], q1_[1], q1_[2], q1_[3], zm9[0], zm9[1]);
          } else {
            mma(a0[0], a0[1], a0[2], a0[3], q0_[0], q0_[1], q0_[2], q0_[3], sg ? zm7[2 * kap] : z09[2 * kap], sg ? zm7[2 * kap + 1] : z09[2 * kap + 1]);
            mma(a1[0], a1[1], a1[2], a1[3], q1_[0], q1_[1], q1_[2], q1_[3], sg ? z07[2 * kap] : zm9[2 * kap], sg ? z07[2 * kap + 1] : zm9[2 * kap + 1]);
          }
        }
    SPLIT();
#pragma unroll
    for (int i = 0; i < 8; i++) {
      uint32_t h[4];
      ldsm4(h, qa + 128 * i);
      const float ci[4] = {a[i >> 1][0][2 * (i & 1)], a[i >> 1][0][2 * (i & 1) + 1], a[i >> 1][1][2 * (i & 1)], a[i >> 1][1][2 * (i & 1) + 1]};
      mmac(acc[8 + i], h[0], h[1], h[2], h[3], lb0, lb1, ci);
    }
  }
  TS(44);
  {
    uint2 a5[10], a3[10];
    const uint32_t aa = tb + T_5 + 4 * (8 + 2 * g - 2 * c);
#pragma unroll
    for (int m = 0; m < 10; m++) { a5[m] = lds64(aa + 32 * m); a3[m] = lds64(aa + 384 + 32 * m); }
    uint32_t x5[12][2], x3[12][2];
    auto ygen = [&](int kap) {
#pragma unroll
      for (int hh = 0; hh < 2; hh++) {
        float y0, y1, y2, y3;
        mma0(y0, y1, y2, y3, by[0], by[1], by[2], by[3], lds32(y0a + 128 * kap + 64 * hh), lds32(y1a + 128 * kap + 64 * hh));
        x5[kap][hh] = pack_bf(y0, y1);
        x3[kap][hh] = pack_bf(y2, y3);
      }
    };
    ygen(11); ygen(10); ygen(9); ygen(8);
#pragma unroll
    for (int kap = 11; kap >= 0; kap--) {
      if (kap >= 4) ygen(kap - 4);
#pragma unroll
      for (int sg = 0; sg < 2; sg++)
#pragma unroll
        for (int i = 4; i >= 0; i--) {
          const int be = kap + 4 + i;
          if (be <= 15) {
            const uint2 &hi = sg ? a3[2 * i + 1] : a5[2 * i + 1], &lo = sg ? a3[2 * i] : a5[2 * i];
            const uint32_t b0 = sg ? x3[kap][0] : x5[kap][0], b1 = sg ? x3[kap][1] : x5[kap][1];
            if (be < 8 && i == 0 && sg == 0) mma0(acc[be][0], acc[be][1], acc[be][2], acc[be][3], hi.x, hi.y, lo.x, lo.y, b0, b1);
            else mma(acc[be][0], acc[be][1], acc[be][2], acc[be][3], hi.x, hi.y, lo.x, lo.y, b0, b1);
          }
        }
    }
  }
  TS(45);
  {
    const uint32_t st = tb + T_ST + lane * 8;
#pragma unroll
    for (int be = 4; be < 12; be++) sts64(st + 256 * be, pack_bf(acc[be][0], acc[be][1]), pack_bf(acc[be][2], acc[be][3]));
    SPLIT();
    uint32_t F[66], qd[8][4];
    const uint32_t fa = tb + T_D + 32 + 4 * x;
#pragma unroll
    for (int i = 0; i < 32; i++) {
      const int s = 120 - (i >> 2) - 8 * (i & 3);
      uint32_t(&q)[4] = qd[i & 7];
      ldsm4(q, qa + 16 * s);
      const int m = 16 * (i & 3) + 2 * (i >> 2);
      F[m] = lds32(fa + 32 * m); F[m + 1] = lds32(fa + 32 * m + 32);
#pragma unroll
      for (int be = 15; be >= 12; be--) {
        const int de = 8 * be - s;
        if (de >= 0) mma(acc[be][0], acc[be][1], acc[be][2], acc[be][3], q[0], q[1], q[2], q[3], F[2 * de + 1], F[2 * de]);
      }
    }
    F[64] = lds32(fa + 32 * 64); F[65] = lds32(fa + 32 * 65);
    uint32_t qp = qa + 128 * 11, sta = st + 256 * 10;
    uint4* yd = ydst + 7 * 32;
#pragma unroll
    for (int i = 0; i < 6; i++) ldsm4(qd[i], qp - 16 * i);
    uint2 sv = lds64(sta + 256);
    float ci[4] = {bf_lo(sv.x), bf_hi(sv.x), bf_lo(sv.y), bf_hi(sv.y)};
    float T[5][4];
#pragma unroll
    for (int i = 0; i < 16; i++) T[i >> 2][i & 3] = acc[12 + (i >> 2)][i & 3];
    nb_sync(NB_YZ, 160);
    TS(46);
#pragma unroll 1
    for (int bp = 5; bp >= 0; bp--) {
      uint32_t held[2];
#pragma unroll
      for (int o = 1; o >= 0; o--) {
#pragma unroll
        for (int k = 4; k >= 1; k--) mmac(T[k], qd[0][0], qd[0][1], qd[0][2], qd[0][3], F[16 * k + 1], F[16 * k], T[k - 1]);
        mmac(T[0], qd[0][0], qd[0][1], qd[0][2], qd[0][3], F[1], F[0], ci);
        ldsm4(qd[6], qp - 16 * 6);
        ldsm4(qd[7], qp - 16 * 7);
        sv = lds64(sta);
#pragma unroll
        for (int i = 1; i < 8; i++) {
#pragma unroll
          for (int k = 3; k >= 0; k--)
            mma(T[k][0], T[k][1], T[k][2], T[k][3], qd[i][0], qd[i][1], qd[i][2], qd[i][3], F[16 * k + 2 * i + 1], F[16 * k + 2 * i]);
          if (i < 7) ldsm4(qd[i - 1], qp - 128 - 16 * (i - 1));
          if (i == 2) {
            const uint32_t w0 = pack_bf(T[4][0], T[4][1]), w1 = pack_bf(T[4][2], T[4][3]);
            if (o) { held[0] = w0; held[1] = w1; }
            else st_x(yd, nz(w0), w1, held[0], held[1]);
          }
          if (i == 4) {
            if (2 * bp + o <= 4) sv = make_uint2(0, 0);
            ci[0] = bf_lo(sv.x); ci[1] = bf_hi(sv.x); ci[2] = bf_lo(sv.y); ci[3] = bf_hi(sv.y);
          }
        }
        qp -= 128; sta -= 256;
      }
      yd -= 32;
    }
#pragma unroll
    for (int B = 1; B >= 0; B--)
      st_x(ydst + B * 32, nz(pack_bf(T[2 * B][0], T[2 * B][1])), pack_bf(T[2 * B][2], T[2 * B][3]),
           pack_bf(T[2 * B + 1][0], T[2 * B + 1][1]), pack_bf(T[2 * B + 1][2], T[2 * B + 1][3]));
  }
}

__device__ __forceinline__ void dual_exp(const uint32_t* w, uint32_t* e) {
  const float L = 1.44268798828125f;
  uint32_t mx = bmax2(bmax2(w[0], w[1]), bmax2(w[2], w[3]));
  uint32_t mn = bmin2(bmin2(w[0], w[1]), bmin2(w[2], w[3]));
  mx = bmax2(mx, __shfl_xor_sync(0xffffffffu, mx, 1));
  mn = bmin2(mn, __shfl_xor_sync(0xffffffffu, mn, 1));
  mx = bmax2(mx, __shfl_xor_sync(0xffffffffu, mx, 2));
  mn = bmin2(mn, __shfl_xor_sync(0xffffffffu, mn, 2));
  const float mx0 = bf_lo(mx) * -L, mx1 = bf_hi(mx) * -L, mn0 = bf_lo(mn) * L, mn1 = bf_hi(mn) * L;
#pragma unroll
  for (int i = 0; i < 2; i++) {
    const float a0 = bf_lo(w[2 * i]), a1 = bf_hi(w[2 * i]), b0 = bf_lo(w[2 * i + 1]), b1 = bf_hi(w[2 * i + 1]);
    e[2 * i] = pack_bf(ex2(fmaf(a0, L, mx0)), ex2(fmaf(b0, L, mx0)));
    e[2 * i + 1] = pack_bf(ex2(fmaf(a1, L, mx1)), ex2(fmaf(b1, L, mx1)));
    e[4 + 2 * i] = pack_bf(ex2(fmaf(a0, -L, mn0)), ex2(fmaf(b0, -L, mn0)));
    e[5 + 2 * i] = pack_bf(ex2(fmaf(a1, -L, mn1)), ex2(fmaf(b1, -L, mn1)));
  }
}
__device__ __forceinline__ void normalise(uint32_t* e, const float (&s)[4]) {
  const uint32_t r = pack_bf(rcp(s[0]), rcp(s[2]));
  const __nv_bfloat162 rr = *(const __nv_bfloat162*)&r;
#pragma unroll
  for (int i = 0; i < 4; i++) {
    const __nv_bfloat162 v = __hmul2(*(const __nv_bfloat162*)&e[i], (i & 1) ? __high2bfloat162(rr) : __low2bfloat162(rr));
    e[i] = *(const uint32_t*)&v;
  }
}
__host__ __device__ constexpr uint64_t qdesc(uint32_t addr) { return mkdesc(addr, 128, 256, 0); }

__global__ void __launch_bounds__(NTHREADS, 1)
fused_kernel(const Params P, const __grid_constant__ CUtensorMap mx, const __grid_constant__ CUtensorMap mw,
             const __grid_constant__ CUtensorMap mo, const __grid_constant__ CUtensorMap mu,
             const __grid_constant__ CUtensorMap mout, const __grid_constant__ CUtensorMap mw4) {
  constexpr uint32_t sb = SB;
  const int tid = threadIdx.x, lane = tid & 31;
  const int warp = __shfl_sync(0xffffffffu, tid >> 5, 0);
  const int b = blockIdx.x, oct = b >> 3, i8 = b & 7;
  const int rt = oct < 8 ? oct : 15 - oct;
  const int hp = (oct >> 3) * 8 + i8;

  const int wg = warp >> 2, w = warp & 3;
  const int d = b * 4 + ((tid >> 5) & 3);
  if (tid < 384) {
    asm volatile("prefetch.tensormap [%0];" ::"l"(&mu) : "memory");
    asm volatile("prefetch.tensormap [%0];" ::"l"(&mw) : "memory");
    asm volatile("prefetch.tensormap [%0];" ::"l"(&mx) : "memory");
    asm volatile("prefetch.tensormap [%0];" ::"l"(&mw4) : "memory");
  }
  if (warp == 12) {
    if (lane == 0) {
#pragma unroll
      for (int i = 0; i < 9; i++) mbar_init(BAR(i), 1);
      asm volatile("fence.mbarrier_init.release.cluster;" ::: "memory");
    }
    __syncwarp();
    if (lane < 9) mbar_expect(BAR(0) + 8 * lane, lane == 5 ? 65536 : ((lane == 0 || lane > 5) ? 16384 : 28672));
    __syncwarp();
    e_tma3d(sb + OFF_W, &mw, BAR(MB_FULL), hp * 32, 0, 0);
    e_tma2d(sb + OFF_X + 3 * 16384, &mx, BAR(MB_FULL), 0, rt * 256);
  } else if (warp == 13) {
    if (lane == 0) {
#pragma unroll
      for (int i = 9; i < 39; i++) mbar_init(BAR(i), i < MB_EMPTY ? 1 : (i < MB_AUX ? 4 : 8));
      asm volatile("fence.mbarrier_init.release.cluster;" ::: "memory");
    }
    __syncwarp();
    if (lane < 9) mbar_expect(BAR(MB_FULL + 8) + 8 * lane, lane < 8 ? 16384 : 131072);
  }
  const KgenRaw raw = kgen_load(P, d, tid >> 7, lane);
  const unsigned short dsk = __ldg((const unsigned short*)P.Dskip + d);
  const uint32_t tb = sb + OFF_T + w * T_CH;
  const uint32_t kp = wg >= 2 ? sb + OFF_STG0 + 16384 + w * 2048 : ((tb + 127) & ~127u) + wg * 2048;
  const KgenAddr kad = kgen_addr(lane, wg == 3 ? sb + OFF_X + 32768 + w * 2048 : kp);
  if (warp == 12) {
#pragma unroll 1
    for (int kb = 1; kb < 4; kb++) {
      if (kb == U_AT) e_tma5d(sb + OFF_STG0, &mu, BAR(MB_URAW), i8 * 64, oct * 4);
      e_tma3d(sb + OFF_W + kb * 12288, &mw, BAR(MB_FULL) + 8 * kb, hp * 32, kb * 64, 0);
      e_tma2d(sb + OFF_X + (kb < 2 ? kb + 3 : kb - 2) * 16384, &mx, BAR(MB_FULL) + 8 * kb, kb * 64, rt * 256);
    }
    e_prefetch(P.x + (size_t)(rt * 256 + hp * 16) * 512, 16384);
    e_tma4d(sb + OFF_W + 4 * 12288, &mw4, BAR(MB_FULL + 4), hp * 32, 4);
    if (smem_u32(smem_raw) != SB) __trap();
    if (lane == 0) TS1(54);
  }
  float k[5][4], k2048, ksc;
  kgen_unit(raw, kad, blockIdx.y, k, k2048, ksc);
  TS(40 + wg);
  if ((fu(k[0][0]) & fu(k[1][0]) & fu(k[2][0]) & fu(k[3][0]) & fu(k[4][0])) == 0xffffffffu) sts32(kp, 0);
  if (wg == 3) {
    nb_sync(0, 512);
    if (warp == 12) {
      asm volatile("fence.proxy.async.shared::cta;" ::: "memory");
      e_tma2d(sb + OFF_X + 2 * 16384, &mx, BAR(MB_FULL + 4), 256, rt * 256);
    }
  } else if (wg) {
    nb_arrive(0, 512);
  }
  k2048 += __shfl_xor_sync(0xffffffffu, k2048, 16);
  k2048 += __shfl_xor_sync(0xffffffffu, k2048, 8);
  if (wg != 2) {
    uint32_t h[10];
#pragma unroll
    for (int j = 0; j < 10; j++) h[j] = hu(__floats2half2_rn(k[j >> 1][2 * (j & 1)], k[j >> 1][2 * (j & 1) + 1]));
    sts128(kp + lane * 16, h[0], h[1], h[2], h[3]);
    sts128(kp + 512 + lane * 16, h[4], h[5], h[6], h[7]);
    sts128(kp + 1024 + lane * 16, h[8], h[9], fu(k2048), fu(ksc));
  }
  if (wg == 0) { nb_arrive(NB_PREP, 512); nb_sync(0, 512); }
  else if (wg == 3) nb_arrive(NB_PREP, 512);
  else nb_sync(NB_PREP, 512);
  if (warp >= 12) {
    asm volatile("setmaxnreg.dec.sync.aligned.u32 32;");
    if (warp == 12) {
      uint32_t slot = sb + OFF_X + 3 * 16384;
#pragma unroll 1
      for (int n = 0; n < 11; n++) {
        mbar_spin(BAR(MB_EMPTY) + 8 * n);
        const int m = n + 5;
        e_tma2d(slot, &mx, BAR(MB_FULL) + 8 * m, (m & 7) * 64, rt * 256 + (m >> 3) * 128);
        slot = slot == sb + OFF_X + 4 * 16384 ? sb + OFF_X : slot + 16384;
        if (n == 7) e_prefetch(P.wo + (size_t)b * 2048, 4096);
      }
#pragma unroll 1
      for (int i = 0; i < 8; i++) {
        mbar_wait(BAR(MB_EMPTY + 10) + 8 * ((0x54332100u >> (4 * i)) & 7));
        const int w0 = (0x54736210u >> (4 * i)) & 7;
        e_tma3d(sb + OFF_W + w0 * 16384, &mo, BAR(MB_WO), 0, w0 * 64, (hp & 3) * 2);
      }
    } else {
      if (warp == 15) {
        const uint4 v0 = __ldg((const uint4*)P.wphi + hp * 64 + lane), v1 = __ldg((const uint4*)P.wphi + hp * 64 + 32 + lane);
        sts128(sb + OFF_PHI + (lane & 1) * 256 + (lane >> 1) * 16, v0.x, v0.y, v0.z, v0.w);
        sts128(sb + OFF_PHI + 512 + (lane & 1) * 256 + (lane >> 1) * 16, v1.x, v1.y, v1.z, v1.w);
        const uint32_t one = (((lane >> 3) ^ (lane >> 4)) & 1) ? 0u : ((lane & 1) ? 0x3F800000u : 0x3F80u);
        const int q = (lane >> 1) & 3;
        sts128(sb + OFF_EYE + lane * 16, q == 0 ? one : 0u, q == 1 ? one : 0u, q == 2 ? one : 0u, q == 3 ? one : 0u);
        sts64(sb + OFF_ONE + lane * 8, 0x3F803F80u, 0x3F803F80u);
        asm volatile("fence.proxy.async.shared::cta;" ::: "memory");
        nb_arrive(NB_KREAD, 160);
        mbar_wait(BAR(MB_EMPTY + ZERO_STEP));
        uint4* py = P.xs + X_Y + b * 1024 + lane;
#pragma unroll 1
        for (int i = 0; i < 1024; i += 32) st_x(py + i, 0, 0, 0, 0);
        nb_arrive(NB_YZ, 160);
        nb_arrive(NB_ODONE, 320);
        if (lane == 0) TS1(55);
        return;
      }
      uint32_t* const cnt = (uint32_t*)(P.xs + X_CNT) + (warp == 13 ? i8 : 8 + rt) * 32;
      const unsigned target = (ld_x32(cnt) & ~15u) + 16;
      if (warp == 13) {
        uint4* pp = P.xs + X_PART + (hp * 8 + rt) * 144 + lane;
#pragma unroll 1
        for (int i = 0; i < 144; i += 32) if (i + lane < 144) st_x(pp + i, 0, 0, 0, 0);
      }
      nb_sync(warp == 13 ? NB_INIT : NB_ODONE, warp == 13 ? 160 : 320);
      if (lane == 0) TS1(warp == 13 ? 49 : 56);
      asm volatile("fence.proxy.async.shared::cta;" ::: "memory");
      if (lane == 0) asm volatile("red.release.gpu.global.add.u32 [%0], 1;" ::"l"(cnt) : "memory");
      if (lane == 0) TS1(warp == 13 ? 50 : 57);
      const uint32_t* pc = (warp == 13 && (lane & 1)) ? (uint32_t*)(P.xs + X_CNT) + (b >> 4) * 32 : cnt;
#pragma unroll 1
      for (int i = 0; i < SPIN_MAX; i++) {
        unsigned v;
        asm volatile("ld.acquire.gpu.global.u32 %0, [%1];" : "=r"(v) : "l"(pc) : "memory");
        if (__all_sync(0xffffffffu, (int)(v - target) >= 0)) break;
      }
      if (lane == 0) TS1(warp == 13 ? 51 : 58);
      asm volatile("fence.proxy.async.global;" ::: "memory");
      if (warp == 13) {
        mbar_wait(BAR(MB_EMPTY + 11));
        e_expect(BAR(MB_UFULL), 4 * U_CH);
        e_bulk(sb + OFF_U, P.xs + X_UT + b * (U_CH / 4), 4 * U_CH, BAR(MB_UFULL));
      } else {
        const uint4* src = P.xs + X_O + (rt * 4 + (hp >> 2)) * 4096;
        e_expect(BAR(MB_OA), 14336);
        e_bulk(sb + OFF_STG0, src + 3200, 14336, BAR(MB_OA));
        e_expect(BAR(MB_OC), 32768);
        e_bulk(sb + OFF_X + 32768, src, 32768, BAR(MB_OC));
        nb_sync(NB_BDONE, 288);
        asm volatile("fence.proxy.async.shared::cta;" ::: "memory");
        e_expect(BAR(MB_OB), 18432);
        e_bulk(sb + OFF_U, src + 2048, 18432, BAR(MB_OB));
      }
    }
    return;
  }

  const int t = tid & 127;
  const int g = lane >> 2, c = lane & 3;
  {
    if (wg == 2) {
      asm volatile("setmaxnreg.inc.sync.aligned.u32 160;");
#pragma unroll
      for (int j = 0; j < 5; j++) { k[j][0] *= ksc; k[j][1] *= ksc; k[j][2] *= ksc; k[j][3] *= ksc; }
#pragma unroll 1
      for (int q = 0; q < 3; q++) {
        const uint32_t src = (q == 2 ? kp : ((tb + 127) & ~127u) + q * 2048) + lane * 16;
        const uint4 v0 = lds128(src), v1 = lds128(src + 512), v2 = lds128(src + 1024);
        const uint32_t h[10] = {v0.x, v0.y, v0.z, v0.w, v1.x, v1.y, v1.z, v1.w, v2.x, v2.y};
#pragma unroll
        for (int j = 0; j < 10; j++) {
          const float2 f = __half22float2(*(const __half2*)&h[j]);
          k[j >> 1][2 * (j & 1)] = fmaf(f.x, uf(v2.w), k[j >> 1][2 * (j & 1)]);
          k[j >> 1][2 * (j & 1) + 1] = fmaf(f.y, uf(v2.w), k[j >> 1][2 * (j & 1) + 1]);
        }
        k2048 += uf(v2.z);
      }
#pragma unroll
      for (int o2 = 4; o2; o2 >>= 1) k2048 += __shfl_xor_sync(0xffffffffu, k2048, o2);
      if (lane == 0) k[0][0] += bf_lo(dsk);
      __syncwarp();
      if (lane == 0) mbar_arrive(BAR(MB_AUX));
      TS(34);
      build_tables(tb, lane, k, k2048);
      TS(35);
      uint4* const g_y = P.xs + X_Y;
      conv_channel(sb + OFF_U + w * U_CH, tb, lane, g_y + (size_t)d * 256 + lane);
      nb_arrive(NB_BDONE, 288);
      TS(37);
      mbar_wait(BAR(MB_OA));
      const int lam = w * 8 + g;
      const uint4* src = g_y + (size_t)(oct * 32 + c * 8) * 256 + i8 * 32 + lam;
      uint4 v[8];
#pragma unroll 1
      for (int it = 0; it < SPIN_MAX; it++) {
        uint32_t m = 0xffffffffu;
#pragma unroll
        for (int i = 0; i < 8; i++) v[i] = ld_x(src + i * 256);
#pragma unroll
        for (int i = 0; i < 8; i++) m = min(m, v[i].x);
        if (__all_sync(0xffffffffu, m != 0)) break;
      }
      __nv_bfloat16* dst = P.out + (size_t)(i8 * 256 + (lam >> 2) * 16 + (lam & 3) * 2) * 1024 + 512 + oct * 32 + c * 8;
#pragma unroll
      for (int i = 0; i < 8; i++) *(uint4*)(dst + (size_t)((i >> 2) * 128 + ((i >> 1) & 1) * 8 + (i & 1)) * 1024) = tr_row(v, i);
      TS(38);
      GT(63);
      if (w == 0) TSDUMP(32);
      return;
    }
    if (wg == 1) {
      mbar_wait(BAR(MB_URAW));
      TS(48);
      uint4* dst = P.xs + X_UT + (i8 * 64 + g) * (U_CH / 16) + (c & 1) * (U_ODD / 16) + U_PAD / 16 + oct * 8 + w * 2 + (c >> 1);
      uint32_t r[8][4];
#pragma unroll
      for (int i = 0; i < 8; i++) ldsm4t(r[i], sb + OFF_STG0 + w * 4096 + lane * 128 + (((i ^ lane) & 7) << 4));
#pragma unroll
      for (int i = 0; i < 8; i++) dst[i * (U_CH / 2)] = make_uint4(r[i][0], r[i][1], r[i][2], r[i][3]);
      nb_arrive(NB_INIT, 160);
      if (lane == 0) mbar_arrive(BAR(MB_AUX));
      mbar_wait(BAR(MB_EMPTY + 4));
      mbar_spin(BAR(MB_EMPTY + 6));
    }
    TS(wg * 16 + 1);
  }

  float acc[2][48];
  {
    uint32_t fb = BAR(MB_FULL) + 64 * wg;
    uint32_t da = (uint32_t)mkdesc(sb + OFF_X, 16, 0, 0) + (wg ? 1024 : 3072), db = (uint32_t)mkdesc(sb + OFF_W, 4096, 0, 0);
    constexpr uint64_t ha = mkdesc(0, 0, 1024, 1), hb = mkdesc(0, 0, 512, 2);
    mbar_spin(fb);
    TS(wg * 16 + 2);
#pragma unroll 1
    for (int kb = 0; kb < 8; kb++) {
      WG_FENCE();
#pragma unroll
      for (int k = 0; k < 4; k++) {
        wgmma_ss_n96(acc[0], ha | (da + 2 * k), hb | (db + 64 * k), k ? 1 : kb);
        wgmma_ss_n96(acc[1], ha | (da + 2 * k + 512), hb | (db + 64 * k), k ? 1 : kb);
      }
      WG_COMMIT();
      if (kb < 7) mbar_spin(fb + 8);
      WG_WAIT(1);
      if (kb > 0) e_arrive(fb + 8 * (MB_EMPTY - MB_FULL - 1));
      fb += 8; db += 768;
      da = da == (uint32_t)mkdesc(sb + OFF_X + 65536, 16, 0, 0) ? da - 4096 : da + 1024;
    }
    if (wg == 0) nb_sync(NB_KREAD, 160);
    WG_WAIT(0);
    e_arrive(fb + 8 * (MB_EMPTY - MB_FULL - 1));
    mbar_spin(fb + 8 * (MB_EMPTY - MB_FULL - 1));
  }
  TS(wg * 16 + 3);
  asm volatile("setmaxnreg.inc.sync.aligned.u32 160;");

  constexpr uint32_t stg0 = sb + OFF_STG0, stg1 = sb + OFF_X + 32768;
  uint4* const g_part = P.xs + X_PART;
  uint4* const g_o = P.xs + X_O;
  constexpr uint32_t kvs = stg0;
  auto pack8 = [](const float* a) { return make_uint4(pack_bf(a[0], a[1]), pack_bf(a[2], a[3]), pack_bf(a[4], a[5]), pack_bf(a[6], a[7])); };
  auto feat = [&](const uint4 (&af)[4], float (&p)[4][8]) {
    WG_FENCE();
#pragma unroll
    for (int u = 0; u < 4; u++) wgmma_rs_n16(p[u], af[u], qdesc(sb + OFF_PHI + (u & 1) * 512), 0);
    WG_COMMIT();
  };
  auto packp = [](const float (&p)[4][8], uint32_t (&pw)[16]) {
#pragma unroll
    for (int i = 0; i < 16; i++) pw[i] = pack_bf(p[i >> 2][(i & 1) + 2 * (i & 2)], p[i >> 2][(i & 1) + 2 * (i & 2) + 2]);
  };
  auto contract = [&](float (&kc)[20], uint32_t stg, int acc_in) {
    WG_FENCE();
#pragma unroll
    for (int s = 0; s < 8; s++) wgmma_ss_n40(kc, qdesc(stg + s * SLAB), qdesc(stg + s * SLAB + 2048), s ? 1 : acc_in);
    WG_COMMIT();
    WG_WAIT(0);
  };
  uint32_t eq[32];
  float kc[20];
  {
    uint4 af[4], aq[4], vp[4];
    float p[4][8];
#pragma unroll
    for (int u = 0; u < 4; u++) af[u] = pack8(acc[u >> 1] + 16 + 8 * (u & 1));
    feat(af, p);
#pragma unroll
    for (int u = 0; u < 4; u++) { aq[u] = pack8(acc[u >> 1] + 8 * (u & 1)); vp[u] = pack8(acc[u >> 1] + 32 + 8 * (u & 1)); }
    WG_WAIT(0);
    uint32_t pw[16], ek[32];
    packp(p, pw);
#pragma unroll
    for (int u = 0; u < 4; u++) dual_exp(pw + 4 * u, ek + 8 * u);
    TS(wg * 16 + 12);
    float rs[8][4];
    WG_FENCE();
#pragma unroll
    for (int i = 0; i < 8; i++) wgmma_rs_n8(rs[i], make_uint4(ek[4 * i], ek[4 * i + 1], ek[4 * i + 2], ek[4 * i + 3]), qdesc(sb + OFF_ONE), 0);
    WG_COMMIT();
    feat(aq, p);
    WG_WAIT(0);
#pragma unroll
    for (int i = 0; i < 8; i++) normalise(ek + 4 * i, rs[i]);
    packp(p, pw);
#pragma unroll 1
    for (int ph = 0; ph < 2; ph++) {
      if (ph == wg) {
#pragma unroll
        for (int u = 0; u < 4; u++) dual_exp(pw + 4 * u, eq + 8 * u);
      } else {
        mbar_wait(BAR(MB_AUX));
        uint32_t sl = (wg ? stg1 : stg0) + w * SLAB + lane * 16;
        asm volatile("" : "+r"(sl));
#pragma unroll
        for (int i = 0; i < 8; i++) stsm4(sl + (i >> 2) * 4 * SLAB + (i & 3) * 512, ek[4 * i], ek[4 * i + 1], ek[4 * i + 2], ek[4 * i + 3]);
#pragma unroll
        for (int i = 0; i < 4; i++) stsm4(sl + (i >> 1) * 4 * SLAB + 2048 + (i & 1) * 512, vp[i].x, vp[i].y, vp[i].z, vp[i].w);
        sts128(sl + (lane >> 4) * (4 * SLAB - 256) + 3072, 0x3F803F80u, 0x3F803F80u, 0x3F803F80u, 0x3F803F80u);
        asm volatile("fence.proxy.async.shared::cta;" ::: "memory");
        if (wg) nb_arrive(NB_ST0, 256);
        TS(wg * 16 + 13);
      }
    }
  }
  if (wg == 0) {
    uint4* pp = g_part + (size_t)(hp * 8 + rt) * 144 + t;
    uint32_t* pz = (uint32_t*)(pp - t + 128) + w * 16 + c * 8 + g;
    asm volatile("" : "+l"(pp), "+l"(pz));
    nb_sync(NB_WG0, 128);
    contract(kc, stg0, 0);
    mbar_wait(BAR(MB_UFULL));
    TS(15);
    nb_sync(NB_ST0, 256);
    contract(kc, stg1, 1);
    TS(6);
    float kv[8];
#pragma unroll
    for (int i = 0; i < 8; i++) kv[i] = w & 2 ? kc[8 + i] : kc[i];
    st_x(pp, nz(pack_bf(kv[0], kv[1])), pack_bf(kv[2], kv[3]), pack_bf(kv[4], kv[5]), pack_bf(kv[6], kv[7]));
    if (c < 2) st_x32(pz, nz(fu(c ? kc[18] : kc[16])));
    TS(5);
  }
  TS(wg * 16 + 4);
  if (wg == 0) {
    const uint4* ps = g_part + (size_t)hp * 8 * 144 + t;
    const uint32_t* zs = (const uint32_t*)(g_part + (size_t)(hp * 8 + (lane >> 4) * 4) * 144 + 128) + w * 16 + (lane & 15);
    uint4 v[8];
    uint32_t zv[4];
#pragma unroll 1
    for (int it = 0; it < SPIN_MAX; it++) {
#pragma unroll
      for (int i = 0; i < 8; i++) v[i] = ld_x(ps + i * 144);
#pragma unroll
      for (int i = 0; i < 4; i++) zv[i] = ld_x32(zs + i * 576);
      uint32_t m = min(min(zv[0], zv[1]), min(zv[2], zv[3]));
#pragma unroll
      for (int i = 0; i < 8; i++) m = min(m, v[i].x);
      if (__all_sync(0xffffffffu, m != 0)) break;
    }
    float s[8];
    WG_FENCE();
#pragma unroll
    for (int r = 0; r < 8; r++) wgmma_rs_n16(s, v[r], qdesc(sb + OFF_EYE), r);
    WG_COMMIT();
    float zsum = (uf(zv[0]) + uf(zv[1])) + (uf(zv[2]) + uf(zv[3]));
    zsum += __shfl_xor_sync(0xffffffffu, zsum, 16);
    const uint32_t z1 = pack_bf(zsum, 1.f);
    if (lane < 16) sts128(kvs + w * 768 + 512 + lane * 16, z1, z1, z1, z1);
    WG_WAIT(0);
    stsm4(kvs + w * 768 + lane * 16, pack_bf(s[0], s[1]), pack_bf(s[2], s[3]), pack_bf(s[4], s[5]), pack_bf(s[6], s[7]));
    asm volatile("fence.proxy.async.shared::cta;" ::: "memory");
    TS(0);
  }
  nb_sync(NB_KV, 256);
  {
    float n[8][12];
    WG_FENCE();
#pragma unroll
    for (int i = 0; i < 8; i++) wgmma_rs_n24(n[i], make_uint4(eq[4 * i], eq[4 * i + 1], eq[4 * i + 2], eq[4 * i + 3]), qdesc(kvs + (i & 3) * 768), 0);
    WG_COMMIT();
    uint32_t* od = (uint32_t*)(g_o + (size_t)((rt * 4 + wg * 2) * 32 + hp * 2) * 128) + w * 64 + lane;
    WG_WAIT(0);
#pragma unroll
    for (int u = 0; u < 4; u++) {
      float(&np)[12] = n[2 * u];
      const float(&nm)[12] = n[2 * u + 1];
      const float q0 = np[9] * rcp(nm[9]), q1 = np[11] * rcp(nm[11]);
      const float r0 = rcp(fmaf(nm[8], q0, fmaf(np[9], 1e-6f, np[8]))), r1 = rcp(fmaf(nm[10], q1, fmaf(np[11], 1e-6f, np[10])));
#pragma unroll
      for (int i = 0; i < 8; i++) np[i] = fmaf(nm[i], (i & 2) ? q1 : q0, np[i]);
      uint32_t* o = od + (u >> 1) * 16384 + (u & 1) * 512;
      o[0] = pack_bf(np[0] * r0, np[1] * r0);
      o[32] = pack_bf(np[2] * r1, np[3] * r1);
      o[256] = pack_bf(np[4] * r0, np[5] * r0);
      o[288] = pack_bf(np[6] * r1, np[7] * r1);
    }
  }
  TS(wg * 16 + 7);
  nb_arrive(NB_ODONE, 320);
  if (wg) { if (w == 0) TSDUMP(16); return; }
  mbar_wait(BAR(MB_WO));
  mbar_wait(BAR(MB_OA));
  TS(8);
  nb_sync(NB_BDONE, 288);
  TS(9);
  float oc[64];
  {
    constexpr uint64_t ha = mkdesc(0, 0, 128, 0), hb = mkdesc(0, 0, 1024, 1);
    constexpr uint32_t da0 = (uint32_t)mkdesc(stg1, 1024, 0, 0), db0 = (uint32_t)mkdesc(sb + OFF_W, 8192, 0, 0);
#pragma unroll 1
    for (int j = 0; j < 8; j++) {
      const int kb = (j + 7) & 7;
      if ((j & 3) == 1) mbar_spin(j == 1 ? BAR(MB_OC) : BAR(MB_OB));
      WG_FENCE();
#pragma unroll
      for (int k = 0; k < 4; k++) wgmma_ss_n128(oc, ha | (da0 + 512 * kb + 128 * k), hb | (db0 + 1024 * kb + 128 * k), k ? 1 : j);
      WG_COMMIT();
    }
    WG_WAIT(0);
  }
  TS(10);
  nb_sync(NB_WG0, 128);
  const uint32_t ot = sb + OFF_W + w * 4096;
#pragma unroll
  for (int i = 0; i < 16; i += 2)
    stsm4(ot + (i >> 3) * 2048 + (lane & 15) * 128 + (((i + (lane >> 4)) ^ lane) & 7) * 16, pack_bf(oc[4 * i], oc[4 * i + 1]),
          pack_bf(oc[4 * i + 2], oc[4 * i + 3]), pack_bf(oc[4 * i + 4], oc[4 * i + 5]), pack_bf(oc[4 * i + 6], oc[4 * i + 7]));
  asm volatile("fence.proxy.async.shared::cta;" ::: "memory");
  __syncwarp();
  e_store3d(&mout, ot, (rt * 4 + (hp >> 2)) * 64 + w * 16, (hp & 3) * 2);
  TS(wg * 16 + 11);
  GT(61 + wg);
  if (w == 0) TSDUMP(0);
  if (w == 1) TSDUMP(48);
}

typedef CUresult (*EncodeFn)(CUtensorMap*, CUtensorMapDataType, cuuint32_t, void*, const cuuint64_t*, const cuuint64_t*,
                             const cuuint32_t*, const cuuint32_t*, CUtensorMapInterleave, CUtensorMapSwizzle,
                             CUtensorMapL2promotion, CUtensorMapFloatOOBfill);

}

extern "C" void kernel_launch(void* const* d_in, const int* in_sizes, int n_in, void* d_out, int out_size) {
  (void)in_sizes; (void)n_in; (void)out_size;
  void* fn = nullptr;
  cudaDriverEntryPointQueryResult qr;
  cudaGetDriverEntryPoint("cuTensorMapEncodeTiled", &fn, cudaEnableDefault, &qr);
  EncodeFn enc = (EncodeFn)fn;
  CUtensorMap mx, mw, mo, mu, mout, mw4;
  const cuuint32_t es[5] = {1, 1, 1, 1, 1};
  {
    cuuint64_t dims[2] = {512, 2048}, st[1] = {1024};
    cuuint32_t box[2] = {64, 128};
    enc(&mx, CU_TENSOR_MAP_DATA_TYPE_BFLOAT16, 2, d_in[0], dims, st, box, es, CU_TENSOR_MAP_INTERLEAVE_NONE,
        CU_TENSOR_MAP_SWIZZLE_128B, CU_TENSOR_MAP_L2_PROMOTION_L2_128B, CU_TENSOR_MAP_FLOAT_OOB_FILL_NONE);
  }
  {
    cuuint64_t dims[3] = {512, 512, 3}, st[2] = {3072, 1024};
    cuuint32_t box[3] = {32, 64, 3};
    enc(&mw, CU_TENSOR_MAP_DATA_TYPE_BFLOAT16, 3, d_in[1], dims, st, box, es, CU_TENSOR_MAP_INTERLEAVE_NONE,
        CU_TENSOR_MAP_SWIZZLE_64B, CU_TENSOR_MAP_L2_PROMOTION_L2_128B, CU_TENSOR_MAP_FLOAT_OOB_FILL_NONE);
  }
  {
    cuuint64_t dims[3] = {64, 512, 8}, st[2] = {1024, 128};
    cuuint32_t box[3] = {64, 64, 2};
    enc(&mo, CU_TENSOR_MAP_DATA_TYPE_BFLOAT16, 3, d_in[3], dims, st, box, es, CU_TENSOR_MAP_INTERLEAVE_NONE,
        CU_TENSOR_MAP_SWIZZLE_128B, CU_TENSOR_MAP_L2_PROMOTION_L2_128B, CU_TENSOR_MAP_FLOAT_OOB_FILL_NONE);
  }
  {
    cuuint64_t dims[5] = {512, 2, 4, 4, 64}, st[4] = {1024, 8192, 2048, 32768};
    cuuint32_t box[5] = {64, 2, 4, 4, 4};
    enc(&mu, CU_TENSOR_MAP_DATA_TYPE_BFLOAT16, 5, d_in[4], dims, st, box, es, CU_TENSOR_MAP_INTERLEAVE_NONE,
        CU_TENSOR_MAP_SWIZZLE_128B, CU_TENSOR_MAP_L2_PROMOTION_L2_128B, CU_TENSOR_MAP_FLOAT_OOB_FILL_NONE);
  }
  {
    cuuint64_t dims[3] = {64, 2048, 16}, st[2] = {2048, 128};
    cuuint32_t box[3] = {64, 16, 2};
    enc(&mout, CU_TENSOR_MAP_DATA_TYPE_BFLOAT16, 3, d_out, dims, st, box, es, CU_TENSOR_MAP_INTERLEAVE_NONE,
        CU_TENSOR_MAP_SWIZZLE_128B, CU_TENSOR_MAP_L2_PROMOTION_NONE, CU_TENSOR_MAP_FLOAT_OOB_FILL_NONE);
  }
  {
    cuuint64_t dims[4] = {512, 64, 3, 8}, st[3] = {3072, 1024, 64 * 3072};
    cuuint32_t box[4] = {32, 64, 3, 4};
    enc(&mw4, CU_TENSOR_MAP_DATA_TYPE_BFLOAT16, 4, d_in[1], dims, st, box, es, CU_TENSOR_MAP_INTERLEAVE_NONE,
        CU_TENSOR_MAP_SWIZZLE_64B, CU_TENSOR_MAP_L2_PROMOTION_L2_128B, CU_TENSOR_MAP_FLOAT_OOB_FILL_NONE);
  }
  Params P;
  P.x = (const __nv_bfloat16*)d_in[0];
  P.wphi = (const __nv_bfloat16*)d_in[2];
  P.wo = (const __nv_bfloat16*)d_in[3];
  P.logA = (const __nv_bfloat16*)d_in[5];
  P.Aim = (const __nv_bfloat16*)d_in[6];
  P.Cre = (const __nv_bfloat16*)d_in[7];
  P.Cim = (const __nv_bfloat16*)d_in[8];
  P.logdt = (const __nv_bfloat16*)d_in[9];
  P.Dskip = (const __nv_bfloat16*)d_in[10];
  P.out = (__nv_bfloat16*)d_out;
  cudaGetSymbolAddress((void**)&P.xs, g_x);
  P.ts = nullptr;
  cudaFuncSetAttribute(fused_kernel, cudaFuncAttributeMaxDynamicSharedMemorySize, SMEM_BYTES);
  fused_kernel<<<NCTA, NTHREADS, SMEM_BYTES>>>(P, mx, mw, mo, mu, mout, mw4);
}
```

```cpp
#include <cuda_runtime.h>
#include <cuda_bf16.h>
#include <cuda_fp16.h>
#include <cuda.h>
#include <stdint.h>

#define DBG_TS 0

namespace {

constexpr int NTHREADS = 512;
constexpr int NCTA = 128;
constexpr int OFF_W = 0;
constexpr int OFF_X = 98304;
constexpr int OFF_U = OFF_X + 65536;
constexpr int U_CH = 4416, U_ODD = 2240, U_PAD = 128;
constexpr int OFF_STG0 = OFF_U + 18432;
constexpr int SLAB = 3328;
constexpr int OFF_T = OFF_STG0 + 8 * SLAB;
constexpr int T_CH = 5216;
constexpr int T_D = 0;
constexpr int T_5 = 2144;
constexpr int T_3 = T_5 + 384;
constexpr int T_7 = T_5 + 1024;
constexpr int T_9 = T_7 + 320;
constexpr int T_KC = T_9 + 320;
constexpr int T_ST = T_5 - 1024;
constexpr int OFF_PHI = OFF_T + 4 * T_CH;
constexpr int OFF_EYE = OFF_PHI + 1024, OFF_ONE = OFF_EYE + 512;
constexpr int OFF_BAR = OFF_ONE + 256;
constexpr int SMEM_BYTES = OFF_BAR + 512 + 256 * DBG_TS;
constexpr uint32_t SB = 1024;
static_assert(T_KC + 2 * 656 <= T_CH, "table size");
static_assert(SMEM_BYTES <= 232448, "smem");
constexpr int MB_URAW = 0, MB_FULL = 1  , MB_WO = 17, MB_UFULL = 18, MB_OA = 19, MB_OB = 20, MB_OC = 21,
              MB_EMPTY = 22  , MB_AUX = 38;
__host__ __device__ constexpr uint32_t BAR(int i) { return SB + OFF_BAR + 8 * i; }
constexpr int NB_WG0 = 1, NB_ODONE = 2, NB_ST0 = 3  , NB_KV = 5, NB_YZ = 6, NB_INIT = 7, NB_PREP = 8, NB_PROD = 9, NB_KREAD = 10, NB_BDONE = 11, NB_ZERO = 12;
#define U_AT 2
#define ZERO_STEP 15
constexpr int SPIN_MAX = 1 << 16;

constexpr int X_CNT = 0;
constexpr int X_PART = 128;
constexpr int X_O = X_PART + 16 * 8 * 144;
constexpr int X_Y = X_O + 32 * 32 * 128;
constexpr int X_UT = X_Y + 512 * 8 * 32;
constexpr int X_SIZE = X_UT + 512 * (U_CH / 16);
__device__ __align__(128) uint4 g_x[X_SIZE];
extern __shared__ uint8_t smem_raw[];
#define TS(i) do {} while (0)
#define TS1(i) do {} while (0)
#define GT(i) do {} while (0)
#define TSDUMP(base) do {} while (0)

__device__ __forceinline__ uint32_t smem_u32(const void* p) { return (uint32_t)__cvta_generic_to_shared(p); }
__device__ __forceinline__ void mbar_arrive(uint32_t b) {
  asm volatile("mbarrier.arrive.shared::cta.b64 _, [%0];" ::"r"(b) : "memory");
}
__device__ __forceinline__ void mbar_wait(uint32_t b) {
  uint32_t done = 0;
#pragma unroll 1
  for (int i = 0; i < SPIN_MAX && !done; i++) {
    asm volatile("{\n.reg .pred p;\nmbarrier.try_wait.parity.shared::cta.b64 p, [%1], 0, 4000;\nselp.u32 %0, 1, 0, p;\n}\n"
                 : "=r"(done) : "r"(b) : "memory");
  }
}
__device__ __forceinline__ void mbar_spin(uint32_t b) {
  uint32_t done = 0;
#pragma unroll 1
  for (int i = 0; i < (SPIN_MAX << 4) && !done; i++) {
    asm volatile("{\n.reg .pred p;\nmbarrier.try_wait.parity.shared::cta.b64 p, [%1], 0;\nselp.u32 %0, 1, 0, p;\n}\n"
                 : "=r"(done) : "r"(b) : "memory");
  }
}
__device__ __forceinline__ void mbar_init(uint32_t b, int n) {
  asm volatile("mbarrier.init.shared::cta.b64 [%0], %1;" ::"r"(b), "r"(n) : "memory");
}
__device__ __forceinline__ void mbar_expect(uint32_t b, int bytes) {
  asm volatile("mbarrier.arrive.expect_tx.shared::cta.b64 _, [%0], %1;" ::"r"(b), "r"(bytes) : "memory");
}
__device__ __forceinline__ void nb_sync(int id, int n) { asm volatile("bar.sync %0, %1;" ::"r"(id), "r"(n) : "memory"); }
__device__ __forceinline__ void nb_arrive(int id, int n) { asm volatile("bar.arrive %0, %1;" ::"r"(id), "r"(n) : "memory"); }
#define ELECT "{\n.reg .pred p;\nelect.sync _|p, 0xffffffff;\n@p "
__device__ __forceinline__ void e_arrive(uint32_t b) {
  asm volatile(ELECT "mbarrier.arrive.shared::cta.b64 _, [%0];\n}\n" ::"r"(b) : "memory");
}
__device__ __forceinline__ void e_expect(uint32_t b, int bytes) {
  asm volatile(ELECT "mbarrier.arrive.expect_tx.shared::cta.b64 _, [%0], %1;\n}\n" ::"r"(b), "r"(bytes) : "memory");
}
__device__ __forceinline__ void e_tma2d(uint32_t dst, const CUtensorMap* m, uint32_t bar, int c0, int c1) {
  asm volatile(ELECT "cp.async.bulk.tensor.2d.shared::cluster.global.mbarrier::complete_tx::bytes [%0], [%1, {%3,%4}], [%2];\n}\n"
               ::"r"(dst), "l"(m), "r"(bar), "r"(c0), "r"(c1) : "memory");
}
__device__ __forceinline__ void e_tma3d(uint32_t dst, const CUtensorMap* m, uint32_t bar, int c0, int c1, int c2) {
  asm volatile(ELECT "cp.async.bulk.tensor.3d.shared::cluster.global.mbarrier::complete_tx::bytes [%0], [%1, {%3,%4,%5}], [%2];\n}\n"
               ::"r"(dst), "l"(m), "r"(bar), "r"(c0), "r"(c1), "r"(c2) : "memory");
}
__device__ __forceinline__ void e_tma4d(uint32_t dst, const CUtensorMap* m, uint32_t bar, int c0, int c3) {
  asm volatile(ELECT "cp.async.bulk.tensor.4d.shared::cluster.global.mbarrier::complete_tx::bytes [%0], [%1, {%3,%5,%5,%4}], [%2];\n}\n"
               ::"r"(dst), "l"(m), "r"(bar), "r"(c0), "r"(c3), "r"(0) : "memory");
}
__device__ __forceinline__ void e_tma5d(uint32_t dst, const CUtensorMap* m, uint32_t bar, int c0, int c4) {
  asm volatile(ELECT "cp.async.bulk.tensor.5d.shared::cluster.global.mbarrier::complete_tx::bytes [%0], [%1, {%3,%5,%5,%5,%4}], [%2];\n}\n"
               ::"r"(dst), "l"(m), "r"(bar), "r"(c0), "r"(c4), "r"(0) : "memory");
}
__device__ __forceinline__ void e_bulk(uint32_t dst, const void* src, int bytes, uint32_t bar) {
  asm volatile(ELECT "cp.async.bulk.shared::cluster.global.mbarrier::complete_tx::bytes [%0], [%1], %2, [%3];\n}\n"
               ::"r"(dst), "l"(src), "r"(bytes), "r"(bar) : "memory");
}
__device__ __forceinline__ void e_prefetch(const void* p, int bytes) {
  asm volatile(ELECT "cp.async.bulk.prefetch.L2.global [%0], %1;\n}\n" ::"l"(p), "r"(bytes) : "memory");
}
__device__ __forceinline__ void e_store3d(const CUtensorMap* m, uint32_t src, int c1, int c2) {
  asm volatile(ELECT "cp.async.bulk.tensor.3d.global.shared::cta.bulk_group [%0, {%4,%2,%3}], [%1];\n"
               "@p cp.async.bulk.commit_group;\n@p cp.async.bulk.wait_group.read 0;\n}\n"
               ::"l"(m), "r"(src), "r"(c1), "r"(c2), "r"(0) : "memory");
}
__host__ __device__ constexpr uint64_t mkdesc(uint32_t addr, uint32_t lbo, uint32_t sbo, int swz) {
  return (uint64_t)((addr & 0x3FFFF) >> 4) | ((uint64_t)(lbo >> 4) << 16) | ((uint64_t)(sbo >> 4) << 32) |
         ((uint64_t)swz << 62);
}
#define WG_FENCE() asm volatile("wgmma.fence.sync.aligned;" ::: "memory")
#define WG_COMMIT() asm volatile("wgmma.commit_group.sync.aligned;" ::: "memory")
#define WG_WAIT(n) asm volatile("wgmma.wait_group.sync.aligned " #n ";" ::: "memory")

__device__ __forceinline__ void mma(float& d0, float& d1, float& d2, float& d3, uint32_t a0, uint32_t a1, uint32_t a2,
                                    uint32_t a3, uint32_t b0, uint32_t b1) {
  asm volatile("mma.sync.aligned.m16n8k16.row.col.f32.bf16.bf16.f32 {%0,%1,%2,%3},{%4,%5,%6,%7},{%8,%9},{%0,%1,%2,%3};"
               : "+f"(d0), "+f"(d1), "+f"(d2), "+f"(d3)
               : "r"(a0), "r"(a1), "r"(a2), "r"(a3), "r"(b0), "r"(b1));
}
__device__ __forceinline__ void mmac(float (&d)[4], uint32_t a0, uint32_t a1, uint32_t a2, uint32_t a3, uint32_t b0,
                                     uint32_t b1, const float (&c)[4]) {
  asm volatile("mma.sync.aligned.m16n8k16.row.col.f32.bf16.bf16.f32 {%0,%1,%2,%3},{%4,%5,%6,%7},{%8,%9},{%10,%11,%12,%13};"
               : "=f"(d[0]), "=f"(d[1]), "=f"(d[2]), "=f"(d[3])
               : "r"(a0), "r"(a1), "r"(a2), "r"(a3), "r"(b0), "r"(b1), "f"(c[0]), "f"(c[1]), "f"(c[2]), "f"(c[3]));
}
__device__ __forceinline__ void mma_p(int p, float (&d)[4], uint32_t a0, uint32_t a1, uint32_t a2, uint32_t a3, uint32_t b0, uint32_t b1) {
  asm volatile("{\n.reg .pred q;\nsetp.ne.b32 q, %10, 0;\n"
               "@q mma.sync.aligned.m16n8k16.row.col.f32.bf16.bf16.f32 {%0,%1,%2,%3},{%4,%5,%6,%7},{%8,%9},{%0,%1,%2,%3};\n}\n"
               : "+f"(d[0]), "+f"(d[1]), "+f"(d[2]), "+f"(d[3])
               : "r"(a0), "r"(a1), "r"(a2), "r"(a3), "r"(b0), "r"(b1), "r"(p));
}
__device__ __forceinline__ void mmac_p(int p, float (&d)[4], uint32_t a0, uint32_t a1, uint32_t a2, uint32_t a3, uint32_t b0,
                                       uint32_t b1, const float (&c)[4]) {
  asm volatile("{\n.reg .pred q;\nsetp.ne.b32 q, %14, 0;\n"
               "@q mma.sync.aligned.m16n8k16.row.col.f32.bf16.bf16.f32 {%0,%1,%2,%3},{%4,%5,%6,%7},{%8,%9},{%10,%11,%12,%13};\n}\n"
               : "+f"(d[0]), "+f"(d[1]), "+f"(d[2]), "+f"(d[3])
               : "r"(a0), "r"(a1), "r"(a2), "r"(a3), "r"(b0), "r"(b1), "f"(c[0]), "f"(c[1]), "f"(c[2]), "f"(c[3]), "r"(p));
}
__device__ __forceinline__ void mma_h(float (&d)[4], const uint32_t (&a)[4], uint32_t b0, uint32_t b1) {
  asm volatile("mma.sync.aligned.m16n8k16.row.col.f32.f16.f16.f32 {%0,%1,%2,%3},{%4,%5,%6,%7},{%8,%9},{%0,%1,%2,%3};"
               : "+f"(d[0]), "+f"(d[1]), "+f"(d[2]), "+f"(d[3]) : "r"(a[0]), "r"(a[1]), "r"(a[2]), "r"(a[3]), "r"(b0), "r"(b1));
}
__device__ __forceinline__ void mma0(float& d0, float& d1, float& d2, float& d3, uint32_t a0, uint32_t a1, uint32_t a2,
                                     uint32_t a3, uint32_t b0, uint32_t b1) {
  asm volatile("mma.sync.aligned.m16n8k16.row.col.f32.bf16.bf16.f32 {%0,%1,%2,%3},{%4,%5,%6,%7},{%8,%9},{%10,%10,%10,%10};"
               : "=f"(d0), "=f"(d1), "=f"(d2), "=f"(d3)
               : "r"(a0), "r"(a1), "r"(a2), "r"(a3), "r"(b0), "r"(b1), "f"(0.f));
}
__device__ __forceinline__ uint32_t pack_bf(float lo, float hi) {
  uint32_t r;
  asm("cvt.rn.bf16x2.f32 %0, %1, %2;" : "=r"(r) : "f"(hi), "f"(lo));
  return r;
}
__device__ __forceinline__ float bf_lo(uint32_t w) { return __uint_as_float(w << 16); }
__device__ __forceinline__ float bf_hi(uint32_t w) { return __uint_as_float(w & 0xffff0000u); }
__device__ __forceinline__ float bf_round(float x) { return __bfloat162float(__float2bfloat16_rn(x)); }
__device__ __forceinline__ uint32_t bmax2(uint32_t a, uint32_t b) {
  uint32_t r; asm("max.bf16x2 %0, %1, %2;" : "=r"(r) : "r"(a), "r"(b)); return r;
}
__device__ __forceinline__ uint32_t bmin2(uint32_t a, uint32_t b) {
  uint32_t r; asm("min.bf16x2 %0, %1, %2;" : "=r"(r) : "r"(a), "r"(b)); return r;
}
__device__ __forceinline__ float ex2(float x) { float r; asm("ex2.approx.ftz.f32 %0, %1;" : "=f"(r) : "f"(x)); return r; }
__device__ __forceinline__ float rcp(float x) { float r; asm("rcp.approx.ftz.f32 %0, %1;" : "=f"(r) : "f"(x)); return r; }
__device__ __forceinline__ void ldsm4(uint32_t (&r)[4], uint32_t a) {
  asm volatile("ldmatrix.sync.aligned.m8n8.x4.shared.b16 {%0,%1,%2,%3}, [%4];"
               : "=r"(r[0]), "=r"(r[1]), "=r"(r[2]), "=r"(r[3]) : "r"(a) : "memory");
}
__device__ __forceinline__ void ldsm4t(uint32_t (&r)[4], uint32_t a) {
  asm volatile("ldmatrix.sync.aligned.m8n8.x4.trans.shared.b16 {%0,%1,%2,%3}, [%4];"
               : "=r"(r[0]), "=r"(r[1]), "=r"(r[2]), "=r"(r[3]) : "r"(a) : "memory");
}
__device__ __forceinline__ void stsm4(uint32_t a, uint32_t r0, uint32_t r1, uint32_t r2, uint32_t r3) {
  asm volatile("stmatrix.sync.aligned.m8n8.x4.shared.b16 [%0], {%1,%2,%3,%4};"
               ::"r"(a), "r"(r0), "r"(r1), "r"(r2), "r"(r3) : "memory");
}
__device__ __forceinline__ uint32_t lds32(uint32_t a) {
  uint32_t r; asm volatile("ld.shared.u32 %0, [%1];" : "=r"(r) : "r"(a) : "memory"); return r;
}
__device__ __forceinline__ uint32_t lds16(uint32_t a) {
  uint32_t r; asm volatile("{\n.reg .u16 h;\nld.shared.u16 h, [%1];\ncvt.u32.u16 %0, h;\n}\n" : "=r"(r) : "r"(a) : "memory"); return r;
}
__device__ __forceinline__ uint2 lds64(uint32_t a) {
  uint2 r; asm volatile("ld.shared.v2.u32 {%0,%1}, [%2];" : "=r"(r.x), "=r"(r.y) : "r"(a) : "memory"); return r;
}
__device__ __forceinline__ uint4 lds128(uint32_t a) {
  uint4 r;
  asm volatile("ld.shared.v4.u32 {%0,%1,%2,%3}, [%4];" : "=r"(r.x), "=r"(r.y), "=r"(r.z), "=r"(r.w) : "r"(a) : "memory");
  return r;
}
__device__ __forceinline__ void sts32(uint32_t a, uint32_t v) { asm volatile("st.shared.u32 [%0], %1;" ::"r"(a), "r"(v) : "memory"); }
__device__ __forceinline__ void sts16(uint32_t a, uint32_t v) {
  asm volatile("{\n.reg .u16 h;\ncvt.u16.u32 h, %1;\nst.shared.u16 [%0], h;\n}\n" ::"r"(a), "r"(v) : "memory");
}
__device__ __forceinline__ void sts64(uint32_t a, uint32_t x, uint32_t y) {
  asm volatile("st.shared.v2.u32 [%0], {%1,%2};" ::"r"(a), "r"(x), "r"(y) : "memory");
}
__device__ __forceinline__ void sts128(uint32_t a, uint32_t x, uint32_t y, uint32_t z, uint32_t w) {
  asm volatile("st.shared.v4.u32 [%0], {%1,%2,%3,%4};" ::"r"(a), "r"(x), "r"(y), "r"(z), "r"(w) : "memory");
}
__device__ __forceinline__ uint4 ld_x(const uint4* p) {
  uint4 r;
  asm volatile("{\n.reg .b128 t;\nld.relaxed.gpu.global.b128 t, [%4];\nmov.b128 {%0,%1,%2,%3}, t;\n}\n"
               : "=r"(r.x), "=r"(r.y), "=r"(r.z), "=r"(r.w) : "l"(p) : "memory");
  return r;
}
__device__ __forceinline__ uint32_t ld_x32(const uint32_t* p) {
  uint32_t r; asm volatile("ld.relaxed.gpu.global.u32 %0, [%1];" : "=r"(r) : "l"(p) : "memory"); return r;
}
__device__ __forceinline__ void st_x(uint4* p, uint32_t x, uint32_t y, uint32_t z, uint32_t w) {
  asm volatile("{\n.reg .b128 t;\nmov.b128 t, {%1,%2,%3,%4};\nst.relaxed.gpu.global.b128 [%0], t;\n}\n"
               ::"l"(p), "r"(x), "r"(y), "r"(z), "r"(w) : "memory");
}
__device__ __forceinline__ void st_x_p(int p, uint4* a, uint32_t x, uint32_t y, uint32_t z, uint32_t w) {
  asm volatile("{\n.reg .b128 t;\n.reg .pred q;\nsetp.ne.b32 q, %5, 0;\nmov.b128 t, {%1,%2,%3,%4};\n@q st.relaxed.gpu.global.b128 [%0], t;\n}\n"
               ::"l"(a), "r"(x), "r"(y), "r"(z), "r"(w), "r"(p) : "memory");
}
__device__ __forceinline__ void sts64_p(int p, uint32_t a, uint32_t x, uint32_t y) {
  asm volatile("{\n.reg .pred q;\nsetp.ne.b32 q, %3, 0;\n@q st.shared.v2.u32 [%0], {%1,%2};\n}\n" ::"r"(a), "r"(x), "r"(y), "r"(p) : "memory");
}
__device__ __forceinline__ void st_x32(uint32_t* p, uint32_t x) {
  asm volatile("st.relaxed.gpu.global.u32 [%0], %1;" ::"l"(p), "r"(x) : "memory");
}
__device__ __forceinline__ uint32_t nz(uint32_t w) { return max(w, 1u); }
__device__ __forceinline__ uint32_t fu(float x) { return __float_as_uint(x); }
__device__ __forceinline__ float uf(uint32_t x) { return __uint_as_float(x); }

__device__ __forceinline__ void wgmma_ss_n96(float (&d)[48], uint64_t da, uint64_t db, int sc) {
  asm volatile("{\n.reg .pred p;\nsetp.ne.b32 p, %50, 0;\n"
      "wgmma.mma_async.sync.aligned.m64n96k16.f32.bf16.bf16 "
      "{%0,%1,%2,%3,%4,%5,%6,%7,%8,%9,%10,%11,%12,%13,%14,%15,%16,%17,%18,%19,%20,%21,%22,%23,%24,%25,%26,%27,%28,%29,%30,%31,%32,%33,%34,%35,%36,%37,%38,%39,%40,%41,%42,%43,%44,%45,%46,%47}, "
      "%48, %49, p, 1, 1, 0, 1;\n}\n"
      : "+f"(d[0]), "+f"(d[1]), "+f"(d[2]), "+f"(d[3]), "+f"(d[4]), "+f"(d[5]), "+f"(d[6]), "+f"(d[7]),
        "+f"(d[8]), "+f"(d[9]), "+f"(d[10]), "+f"(d[11]), "+f"(d[12]), "+f"(d[13]), "+f"(d[14]), "+f"(d[15]),
        "+f"(d[16]), "+f"(d[17]), "+f"(d[18]), "+f"(d[19]), "+f"(d[20]), "+f"(d[21]), "+f"(d[22]), "+f"(d[23]),
        "+f"(d[24]), "+f"(d[25]), "+f"(d[26]), "+f"(d[27]), "+f"(d[28]), "+f"(d[29]), "+f"(d[30]), "+f"(d[31]),
        "+f"(d[32]), "+f"(d[33]), "+f"(d[34]), "+f"(d[35]), "+f"(d[36]), "+f"(d[37]), "+f"(d[38]), "+f"(d[39]),
        "+f"(d[40]), "+f"(d[41]), "+f"(d[42]), "+f"(d[43]), "+f"(d[44]), "+f"(d[45]), "+f"(d[46]), "+f"(d[47])
      : "l"(da), "l"(db), "r"(sc));
}

__device__ __forceinline__ void wgmma_ss_n128(float (&d)[64], uint64_t da, uint64_t db, int sc) {
  asm volatile("{\n.reg .pred p;\nsetp.ne.b32 p, %66, 0;\n"
      "wgmma.mma_async.sync.aligned.m64n128k16.f32.bf16.bf16 "
      "{%0,%1,%2,%3,%4,%5,%6,%7,%8,%9,%10,%11,%12,%13,%14,%15,%16,%17,%18,%19,%20,%21,%22,%23,%24,%25,%26,%27,%28,%29,%30,%31,%32,%33,%34,%35,%36,%37,%38,%39,%40,%41,%42,%43,%44,%45,%46,%47,%48,%49,%50,%51,%52,%53,%54,%55,%56,%57,%58,%59,%60,%61,%62,%63}, "
      "%64, %65, p, 1, 1, 0, 1;\n}\n"
      : "+f"(d[0]), "+f"(d[1]), "+f"(d[2]), "+f"(d[3]), "+f"(d[4]), "+f"(d[5]), "+f"(d[6]), "+f"(d[7]),
        "+f"(d[8]), "+f"(d[9]), "+f"(d[10]), "+f"(d[11]), "+f"(d[12]), "+f"(d[13]), "+f"(d[14]), "+f"(d[15]),
        "+f"(d[16]), "+f"(d[17]), "+f"(d[18]), "+f"(d[19]), "+f"(d[20]), "+f"(d[21]), "+f"(d[22]), "+f"(d[23]),
        "+f"(d[24]), "+f"(d[25]), "+f"(d[26]), "+f"(d[27]), "+f"(d[28]), "+f"(d[29]), "+f"(d[30]), "+f"(d[31]),
        "+f"(d[32]), "+f"(d[33]), "+f"(d[34]), "+f"(d[35]), "+f"(d[36]), "+f"(d[37]), "+f"(d[38]), "+f"(d[39]),
        "+f"(d[40]), "+f"(d[41]), "+f"(d[42]), "+f"(d[43]), "+f"(d[44]), "+f"(d[45]), "+f"(d[46]), "+f"(d[47]),
        "+f"(d[48]), "+f"(d[49]), "+f"(d[50]), "+f"(d[51]), "+f"(d[52]), "+f"(d[53]), "+f"(d[54]), "+f"(d[55]),
        "+f"(d[56]), "+f"(d[57]), "+f"(d[58]), "+f"(d[59]), "+f"(d[60]), "+f"(d[61]), "+f"(d[62]), "+f"(d[63])
      : "l"(da), "l"(db), "r"(sc));
}

__device__ __forceinline__ void wgmma_ss_n40(float (&d)[20], uint64_t da, uint64_t db, int sc) {
  asm volatile("{\n.reg .pred p;\nsetp.ne.b32 p, %22, 0;\n"
      "wgmma.mma_async.sync.aligned.m64n40k16.f32.bf16.bf16 "
      "{%0,%1,%2,%3,%4,%5,%6,%7,%8,%9,%10,%11,%12,%13,%14,%15,%16,%17,%18,%19}, "
      "%20, %21, p, 1, 1, 1, 1;\n}\n"
      : "+f"(d[0]), "+f"(d[1]), "+f"(d[2]), "+f"(d[3]), "+f"(d[4]), "+f"(d[5]), "+f"(d[6]), "+f"(d[7]),
        "+f"(d[8]), "+f"(d[9]), "+f"(d[10]), "+f"(d[11]), "+f"(d[12]), "+f"(d[13]), "+f"(d[14]), "+f"(d[15]),
        "+f"(d[16]), "+f"(d[17]), "+f"(d[18]), "+f"(d[19])
      : "l"(da), "l"(db), "r"(sc));
}

__device__ __forceinline__ void wgmma_rs_n8(float (&d)[4], const uint4& a, uint64_t db, int sc) {
  asm volatile("{\n.reg .pred p;\nsetp.ne.b32 p, %9, 0;\n"
      "wgmma.mma_async.sync.aligned.m64n8k16.f32.bf16.bf16 "
      "{%0,%1,%2,%3}, "
      "{%4,%5,%6,%7}, %8, p, 1, 1, 1;\n}\n"
      : "+f"(d[0]), "+f"(d[1]), "+f"(d[2]), "+f"(d[3])
      : "r"(a.x), "r"(a.y), "r"(a.z), "r"(a.w), "l"(db), "r"(sc));
}

__device__ __forceinline__ void wgmma_rs_n16(float (&d)[8], const uint4& a, uint64_t db, int sc) {
  asm volatile("{\n.reg .pred p;\nsetp.ne.b32 p, %13, 0;\n"
      "wgmma.mma_async.sync.aligned.m64n16k16.f32.bf16.bf16 "
      "{%0,%1,%2,%3,%4,%5,%6,%7}, "
      "{%8,%9,%10,%11}, %12, p, 1, 1, 1;\n}\n"
      : "+f"(d[0]), "+f"(d[1]), "+f"(d[2]), "+f"(d[3]), "+f"(d[4]), "+f"(d[5]), "+f"(d[6]), "+f"(d[7])
      : "r"(a.x), "r"(a.y), "r"(a.z), "r"(a.w), "l"(db), "r"(sc));
}

__device__ __forceinline__ void wgmma_rs_n24(float (&d)[12], const uint4& a, uint64_t db, int sc) {
  asm volatile("{\n.reg .pred p;\nsetp.ne.b32 p, %17, 0;\n"
      "wgmma.mma_async.sync.aligned.m64n24k16.f32.bf16.bf16 "
      "{%0,%1,%2,%3,%4,%5,%6,%7,%8,%9,%10,%11}, "
      "{%12,%13,%14,%15}, %16, p, 1, 1, 1;\n}\n"
      : "+f"(d[0]), "+f"(d[1]), "+f"(d[2]), "+f"(d[3]), "+f"(d[4]), "+f"(d[5]), "+f"(d[6]), "+f"(d[7]),
        "+f"(d[8]), "+f"(d[9]), "+f"(d[10]), "+f"(d[11])
      : "r"(a.x), "r"(a.y), "r"(a.z), "r"(a.w), "l"(db), "r"(sc));
}

struct Params {
  const __nv_bfloat16 *logA, *Aim, *Cre, *Cim, *logdt, *Dskip, *x, *wphi, *wo;
  __nv_bfloat16* out;
  uint4* xs;
  long long* ts;
};

__device__ __forceinline__ uint4 tr_row(const uint4 (&v)[8], int i) {
  uint32_t o[4];
#pragma unroll
  for (int m = 0; m < 4; m++) {
    const uint4 &ra = v[2 * m], &rb = v[2 * m + 1];
    const int k = i >> 1;
    const uint32_t xa = k == 0 ? ra.x : k == 1 ? ra.y : k == 2 ? ra.z : ra.w;
    const uint32_t xb = k == 0 ? rb.x : k == 1 ? rb.y : k == 2 ? rb.z : rb.w;
    o[m] = __byte_perm(xa, xb, (i & 1) ? 0x7632 : 0x5410);
  }
  return make_uint4(o[0], o[1], o[2], o[3]);
}

struct cpx { float r, i; };
__device__ __forceinline__ cpx csq(cpx a) { return {a.r * a.r - a.i * a.i, 2.f * (a.r * a.i)}; }
__device__ __forceinline__ cpx polar(float e, float t) {
  const float m = ex2(e);
  return {m * __cosf(t), m * __sinf(t)};
}

struct KgenRaw { unsigned short la, ai, cr, ci, ldt; };
__device__ __forceinline__ KgenRaw kgen_load(const Params& P, int d, int unit, int lane) {
  const int o = d * 128 + unit * 32 + lane;
  return {__ldg((const unsigned short*)P.logA + o), __ldg((const unsigned short*)P.Aim + o), __ldg((const unsigned short*)P.Cre + o),
          __ldg((const unsigned short*)P.Cim + o), __ldg((const unsigned short*)P.logdt + d)};
}
struct hmul { __half2 a, b; };
__device__ __forceinline__ hmul mk_mul(cpx w) {
  uint32_t b;
  asm("{\n.reg .f32 n;\nneg.ftz.f32 n, %1;\ncvt.rn.f16x2.f32 %0, %2, n;\n}\n" : "=r"(b) : "f"(w.i), "f"(w.r));
  return {__floats2half2_rn(w.r, w.i), *(const __half2*)&b};
}
__device__ __forceinline__ __half2 hcm(__half2 z, const hmul& w) { return __hfma2(__high2half2(z), w.b, __hmul2(__low2half2(z), w.a)); }
__device__ __forceinline__ uint32_t hu(__half2 v) { return *(const uint32_t*)&v; }

struct KgenAddr { uint32_t sa, sb, lb, lc, la; };
__device__ __forceinline__ KgenAddr kgen_addr(int lane, uint32_t buf) {
  KgenAddr a;
  a.sa = buf + (lane & 7) * 128 + ((((lane >> 3) ^ lane) & 7) << 4);
  a.lb = buf + (lane >> 3) * 128 + (((lane ^ (lane >> 3)) & 7) << 4);
  a.la = buf + ((lane >> 3) & 1) * 1024 + (lane >> 4) * 128 + (((lane ^ (lane >> 4)) & 7) << 4);
  a.sb = a.sa ^ 64; a.lc = a.lb ^ 64;
  asm volatile("" : "+r"(a.sa), "+r"(a.sb), "+r"(a.lb), "+r"(a.lc), "+r"(a.la));
  return a;
}
__device__ __forceinline__ void kgen_unit(const KgenRaw& r, const KgenAddr& ad, uint32_t zero, float (&k)[5][4], float& k2048, float& sc) {
  const float dt = bf_round(expf(bf_lo(r.ldt)));
  const float a2 = bf_round(ex2(bf_lo(r.la) * 1.4426950408889634f)) * (dt * -1.4426950408889634f);
  const float f = bf_lo(r.ai) * dt;
  const float r128 = f * 20.371832715762604f;
  const uint32_t ex = min(max(__reduce_max_sync(0xffffffffu, max(r.cr & 0x7fffu, r.ci & 0x7fffu)) >> 7, 1u), 253u);
  const float cs = uf((254u - ex) << 23);
  sc = 2.f * dt * uf(ex << 23);
  const cpx C = {bf_lo(r.cr) * cs, -bf_lo(r.ci) * cs};
  auto put = [&](const __half2 (&v)[8], uint32_t off) {
    stsm4(ad.sa + off, hu(v[0]), hu(v[1]), hu(v[2]), hu(v[3]));
    stsm4(ad.sb + off, hu(v[4]), hu(v[5]), hu(v[6]), hu(v[7]));
  };
  uint32_t A[4][4], B[5][2][4];
  auto get = [&](int j, uint32_t off) {
    __syncwarp();
    ldsm4(B[j][0], ad.lb + off);
    ldsm4(B[j][1], ad.lc + 512 + off);
  };
  auto tile = [&](int j) {
    k[j][0] = k[j][1] = k[j][2] = k[j][3] = 0.f;
#pragma unroll
    for (int s = 0; s < 4; s++) mma_h(k[j], A[s], B[j][s >> 1][2 * (s & 1)], B[j][s >> 1][2 * (s & 1) + 1]);
  };
  auto after = [&](cpx v, uint32_t dep) { return cpx{uf(fu(v.r) ^ (dep & zero)), v.i}; };
  const cpx w1 = polar(a2, f), w128 = polar(a2 * 128.f, (r128 - rintf(r128)) * 6.283185307179586f);
  const cpx w2 = csq(w1), w4 = csq(w2);
  __half2 t0[8], t1[8], t2[8], t3[8], t4[8];
  const hmul m2 = mk_mul(w2), m4 = mk_mul(w4), m128 = mk_mul(w128);
  t0[0] = __floats2half2_rn(1.f, 0.f); t0[1] = __floats2half2_rn(w1.r, w1.i); t0[2] = m2.a; t0[4] = m4.a;
  t0[3] = hcm(t0[1], m2); t0[5] = hcm(t0[1], m4); t0[6] = hcm(t0[2], m4); t0[7] = hcm(t0[3], m4);
  put(t0, 0); get(0, 0);
  t1[0] = m128.a;
#pragma unroll
  for (int i = 1; i < 8; i++) t1[i] = hcm(t0[i], m128);
  put(t1, 1024); get(1, 1024);
  {
    cpx w8 = csq(after(w4, B[0][0][0]));
    w8.i = -w8.i;
    const cpx w16 = csq(w8), w32 = csq(w16), w64 = csq(w32);
    const hmul m8 = mk_mul(w8), m16 = mk_mul(w16), m32 = mk_mul(w32), m64 = mk_mul(w64);
    __half2 a[8];
    a[0] = __floats2half2_rn(C.r, C.i); a[1] = hcm(a[0], m8);
    a[2] = hcm(a[0], m16); a[3] = hcm(a[1], m16);
#pragma unroll
    for (int i = 0; i < 4; i++) a[4 + i] = hcm(a[i], m32);
    put(a, 0);
#pragma unroll
    for (int i = 0; i < 8; i++) a[i] = hcm(a[i], m64);
    put(a, 1024);
    __syncwarp();
#pragma unroll
    for (int s = 0; s < 4; s++) ldsm4(A[s], (ad.la ^ (s << 5)) + s * 256);
  }
  const cpx w256 = csq(after(w128, B[1][0][0]));
  const hmul m256 = mk_mul(w256);
  t2[0] = m256.a;
#pragma unroll
  for (int i = 1; i < 8; i++) t2[i] = hcm((i & 1) ? t1[i & 6] : t0[i & 6], m256);
  put(t2, 0); get(2, 0);
  tile(0); tile(1);
  const cpx w512 = csq(after(w256, A[0][0]));
  const hmul m512 = mk_mul(w512);
  t3[0] = m512.a;
#pragma unroll
  for (int i = 1; i < 8; i++) t3[i] = hcm((i & 2) ? t2[i & 5] : ((i & 1) ? t1[i & 4] : t0[i & 4]), m512);
  put(t3, 1024); get(3, 1024);
  tile(2);
  const cpx w1024 = csq(after(w512, B[2][0][0])), we = csq(w1024);
  const hmul m1024 = mk_mul(w1024);
  t4[0] = m1024.a;
#pragma unroll
  for (int i = 1; i < 8; i++) t4[i] = hcm((i & 4) ? t3[i & 3] : ((i & 2) ? t2[i & 1] : t1[0]), m1024);
  put(t4, 0); get(4, 0);
  tile(3); tile(4);
  k2048 = (C.r * we.r + C.i * we.i) * sc;
}

__device__ __forceinline__ void build_tables(uint32_t tb, int lane, float (&k)[5][4], float k2048) {
  const int g = lane >> 2, c = lane & 3;
  const uint32_t kc = tb + T_KC + 16;
  {
    const uint32_t a0 = kc + 16 * g + 4 * c, a2 = kc + 2 * (256 + 4 * g + c);
    const uint32_t a3 = kc + 2 * (384 + 2 * g + 64 * (c & 1) + (c >> 1)), a4 = kc + 2 * (512 + g + 32 * c);
#pragma unroll
    for (int r = 0; r < 2; r++) {
      sts32(a0 + 128 * r, pack_bf(k[0][2 * r], k[0][2 * r + 1]));
      sts32(a0 + 128 * r + 256, pack_bf(k[1][2 * r], k[1][2 * r + 1]));
      const uint32_t w2 = pack_bf(k[2][2 * r], k[2][2 * r + 1]);
      const uint32_t w3 = pack_bf(k[3][2 * r], k[3][2 * r + 1]);
      const uint32_t w4 = pack_bf(k[4][2 * r], k[4][2 * r + 1]);
      sts16(a2 + 64 * r, w2); sts16(a2 + 64 * r + 128, w2 >> 16);
      sts16(a3 + 32 * r, w3); sts16(a3 + 32 * r + 64, w3 >> 16);
      sts16(a4 + 16 * r, w4); sts16(a4 + 16 * r + 32, w4 >> 16);
    }
  }
  if (lane == 0) { sts16(kc + 2 * 640, pack_bf(k2048, 0.f)); sts32(kc - 4, 0); }
  __syncwarp();
  const uint32_t td = tb + T_D + 32;
#pragma unroll
  for (int hf = 0; hf < 2; hf++) {
    const uint2 v = lds64(kc + 256 * hf + 8 * lane);
    const uint32_t pv = lds32(kc + 256 * hf + 8 * lane - 4);
    sts128(td + 512 * hf + 16 * lane, __byte_perm(v.x, pv, 0x7610), __byte_perm(v.x, v.x, 0x1032), __byte_perm(v.y, v.x, 0x7610),
           __byte_perm(v.y, v.y, 0x1032));
  }
#pragma unroll
  for (int hf = 0; hf < 2; hf++) {
    const uint32_t v = lds32(kc + 512 + 128 * hf + 4 * lane), nx = lds32(kc + 516 + 128 * hf + 4 * lane);
    uint32_t w0 = __byte_perm(v, v, 0x1010);
    const uint32_t w1 = w0;
    if (hf == 0) { const uint32_t pv = lds32(kc + 508); if (lane == 0) w0 = __byte_perm(v, pv, 0x7610); }
    sts128(td + 1024 + 512 * hf + 16 * lane, w0, w1, __byte_perm(v, v, 0x1032), __byte_perm(nx, v, 0x7610));
  }
  {
    const uint32_t kk = lds16(kc + 2 * 384);
    const uint32_t w = lane < 3 ? (kk | (kk << 16)) : (lane == 3 ? (kk << 16) : 0u);
    if (lane < 24) sts32(td + 4 * (lane < 16 ? 512 + lane : lane - 24), w);
    const uint32_t lo_ = lds16(kc + 2 * 511), le_ = lds16(kc + 2 * 512);
    const uint32_t ja = tb + T_5 + (lane < 16 ? 4 * lane : 256 + 4 * lane);
    sts32(ja, lane == 16 ? (le_ << 16) : 0u);
    sts32(ja + 384, lane == 16 ? (lo_ << 16) : 0u);
    sts32(tb + (lane < 16 ? T_7 : T_9 - 64) + 4 * lane, 0u);
  }
#pragma unroll
  for (int s = 0; s < 2; s++) {
    const uint32_t b = kc + 2 * (s ? 512 : 384) + 8 * lane;
    const uint2 v = lds64(b);
    uint32_t em = lds16(b - 2), e0 = v.x;
    const uint32_t e4 = lds16(b + 8);
    if (lane == 0) { em = 0; e0 = 0; }
    sts64(tb + (s ? T_7 : T_3) + 64 + 8 * lane, __byte_perm(v.x, em, 0x5432), __byte_perm(v.y, v.x, 0x7632));
    sts64(tb + (s ? T_9 : T_5) + 64 + 8 * lane, __byte_perm(v.y, e0, 0x5410), __byte_perm(e4, v.y, 0x5410));
  }
  __syncwarp();
}

__device__ __forceinline__ uint32_t box2w(int lo, int n, int o) {
  return ((unsigned)(o - lo) < (unsigned)n ? 0x3F80u : 0u) | ((unsigned)(o + 1 - lo) < (unsigned)n ? 0x3F800000u : 0u);
}

#define SPLIT() asm volatile("{\n.reg .pred p;\nsetp.ne.u32 p, %0, 0;\n@p exit;\n}\n" ::"r"(blockIdx.y) : "memory")

__device__ __forceinline__ void conv_channel(uint32_t ub, uint32_t tb, int lane, uint4* ydst) {
  const int g = lane >> 2, c = lane & 3, x = g - 2 * c;
  const int mi = lane >> 3;
  const uint32_t qa = ub + U_PAD + 16 * (lane & 7) + ((mi == 0 || mi == 3) ? U_ODD : 0) - (mi == 0 ? 16 : 0);
  const uint32_t hb = ub + U_PAD + (mi & 1) * U_ODD + 16 * ((lane >> 4) + (lane & 7)) - 16;
  const uint32_t kv = lds16(tb + T_KC + 16 + 2 * 512);
  const int oh = c < 2 ? 8 + 2 * c : 2 * c - 8, og = c < 3 ? 2 * c : -10;
  uint32_t bx[4] = {box2w(g - 4, 9, 2 * c), box2w(g - 3, 7, 2 * c), box2w(g - 4, 9, oh), box2w(g - 3, 7, oh)};
  uint32_t by[4] = {box2w(g - 10, 5, 2 * c - 8), box2w(g - 5, 3, 2 * c - 8), box2w(g - 10, 5, og), box2w(g - 5, 3, og)};
  uint32_t lb0 = ((unsigned)(x + 5) < 2u ? kv : 0u) | ((unsigned)(x + 4) < 2u ? kv << 16 : 0u);
  uint32_t lb1 = ((unsigned)(x - 3) < 2u ? kv : 0u) | ((unsigned)(x - 4) < 2u ? kv << 16 : 0u);
  const int q0 = g - 1, q1 = c < 3 ? g : g - 2;
  uint32_t y0a = ub + U_PAD + (q0 & 1) * U_ODD + 16 * (q0 >> 1) + 4 * c;
  uint32_t y1a = ub + U_PAD + (q1 & 1) * U_ODD + 16 * (q1 >> 1) + 4 * c;
#pragma unroll
  for (int i = 0; i < 4; i++) asm volatile("" : "+r"(bx[i]), "+r"(by[i]));
  asm volatile("" : "+r"(lb0), "+r"(lb1), "+r"(y0a), "+r"(y1a));
  mbar_wait(BAR(MB_UFULL));
  mbar_wait(BAR(MB_EMPTY + 15));
  TS(36);
  float acc[16][4];
  {
    uint32_t z09[8], z07[8], zm9[8], zm7[8];
#pragma unroll
    for (int i = 0; i < 8; i++) {
      uint32_t h[4];
      ldsm4(h, hb + 128 * i);
      float y0, y1, y2, y3, w0, w1, w2, w3;
      mma0(y0, y1, y2, y3, bx[0], bx[1], bx[2], bx[3], h[2], c < 2 ? h[3] : h[1]);
      mma0(w0, w1, w2, w3, bx[0], bx[1], bx[2], bx[3], h[1], c < 2 ? h[2] : h[0]);
      z09[i] = pack_bf(y0, y1); z07[i] = pack_bf(y2, y3);
      zm9[i] = pack_bf(w0, w1); zm7[i] = pack_bf(w2, w3);
    }
  uint32_t f3[3][4][4];
  {
    const uint32_t fa = tb + T_7 + 4 * (16 + x);
#pragma unroll
    for (int tt = 0; tt < 3; tt++)
#pragma unroll
      for (int D = 0; D < 4; D++) {
        const uint32_t a = fa + (tt == 0 ? 316 : (tt == 1 ? 320 : 0)) + 64 * D;
        f3[tt][D][0] = lds32(a); f3[tt][D][1] = lds32(a + 32); f3[tt][D][2] = lds32(a - 32); f3[tt][D][3] = lds32(a);
      }
  }
    float a[4][2][4];
#pragma unroll
    for (int kap = 0; kap < 4; kap++)
#pragma unroll
      for (int sg = 0; sg < 2; sg++)
#pragma unroll
        for (int bk = 3; bk >= kap; bk--) {
          const uint32_t(&q0_)[4] = f3[sg ? 2 : 0][bk - kap];
          const uint32_t(&q1_)[4] = f3[sg ? 2 : 1][bk - kap];
          float(&a0)[4] = a[bk][0];
          float(&a1)[4] = a[bk][1];
          if (sg == 0 && kap == 0) {
            mma0(a0[0], a0[1], a0[2], a0[3], q0_[0], q0_[1], q0_[2], q0_[3], z09[0], z09[1]);
            mma0(a1[0], a1[1], a1[2], a1[3], q1_[0], q1_[1], q1_[2], q1_[3], zm9[0], zm9[1]);
          } else {
            mma(a0[0], a0[1], a0[2], a0[3], q0_[0], q0_[1], q0_[2], q0_[3], sg ? zm7[2 * kap] : z09[2 * kap], sg ? zm7[2 * kap + 1] : z09[2 * kap + 1]);
            mma(a1[0], a1[1], a1[2], a1[3], q1_[0], q1_[1], q1_[2], q1_[3], sg ? z07[2 * kap] : zm9[2 * kap], sg ? z07[2 * kap + 1] : zm9[2 * kap + 1]);
          }
        }
    SPLIT();
#pragma unroll
    for (int i = 0; i < 8; i++) {
      uint32_t h[4];
      ldsm4(h, qa + 128 * i);
      const float ci[4] = {a[i >> 1][0][2 * (i & 1)], a[i >> 1][0][2 * (i & 1) + 1], a[i >> 1][1][2 * (i & 1)], a[i >> 1][1][2 * (i & 1) + 1]};
      mmac(acc[8 + i], h[0], h[1], h[2], h[3], lb0, lb1, ci);
    }
  }
  TS(44);
  {
    uint2 a5[10], a3[10];
    const uint32_t aa = tb + T_5 + 4 * (8 + 2 * g - 2 * c);
#pragma unroll
    for (int m = 0; m < 10; m++) { a5[m] = lds64(aa + 32 * m); a3[m] = lds64(aa + 384 + 32 * m); }
    uint32_t x5[12][2], x3[12][2];
    auto ygen = [&](int kap) {
#pragma unroll
      for (int hh = 0; hh < 2; hh++) {
        float y0, y1, y2, y3;
        mma0(y0, y1, y2, y3, by[0], by[1], by[2], by[3], lds32(y0a + 128 * kap + 64 * hh), lds32(y1a + 128 * kap + 64 * hh));
        x5[kap][hh] = pack_bf(y0, y1);
        x3[kap][hh] = pack_bf(y2, y3);
      }
    };
    ygen(11); ygen(10); ygen(9); ygen(8);
#pragma unroll
    for (int kap = 11; kap >= 0; kap--) {
      if (kap >= 4) ygen(kap - 4);
#pragma unroll
      for (int sg = 0; sg < 2; sg++)
#pragma unroll
        for (int i = 4; i >= 0; i--) {
          const int be = kap + 4 + i;
          if (be <= 15) {
            const uint2 &hi = sg ? a3[2 * i + 1] : a5[2 * i + 1], &lo = sg ? a3[2 * i] : a5[2 * i];
            const uint32_t b0 = sg ? x3[kap][0] : x5[kap][0], b1 = sg ? x3[kap][1] : x5[kap][1];
            if (be < 8 && i == 0 && sg == 0) mma0(acc[be][0], acc[be][1], acc[be][2], acc[be][3], hi.x, hi.y, lo.x, lo.y, b0, b1);
            else mma(acc[be][0], acc[be][1], acc[be][2], acc[be][3], hi.x, hi.y, lo.x, lo.y, b0, b1);
          }
        }
    }
  }
  TS(45);
  {
    const uint32_t st = tb + T_ST + lane * 8;
#pragma unroll
    for (int be = 4; be < 12; be++) sts64(st + 256 * be, pack_bf(acc[be][0], acc[be][1]), pack_bf(acc[be][2], acc[be][3]));
    SPLIT();
    uint32_t F[66], qd[8][4];
    const uint32_t fa = tb + T_D + 32 + 4 * x;
#pragma unroll
    for (int i = 0; i < 32; i++) {
      const int s = 120 - (i >> 2) - 8 * (i & 3);
      uint32_t(&q)[4] = qd[i & 7];
      ldsm4(q, qa + 16 * s);
      const int m = 16 * (i & 3) + 2 * (i >> 2);
      F[m] = lds32(fa + 32 * m); F[m + 1] = lds32(fa + 32 * m + 32);
#pragma unroll
      for (int be = 15; be >= 12; be--) {
        const int de = 8 * be - s;
        if (de >= 0) mma(acc[be][0], acc[be][1], acc[be][2], acc[be][3], q[0], q[1], q[2], q[3], F[2 * de + 1], F[2 * de]);
      }
    }
    F[64] = lds32(fa + 32 * 64); F[65] = lds32(fa + 32 * 65);
    uint32_t qp = qa + 128 * 11, sta = st + 256 * 10;
    uint4* yd = ydst + 7 * 32;
#pragma unroll
    for (int i = 0; i < 6; i++) ldsm4(qd[i], qp - 16 * i);
    uint2 sv = lds64(sta + 256);
    float ci[4] = {bf_lo(sv.x), bf_hi(sv.x), bf_lo(sv.y), bf_hi(sv.y)};
    float T[5][4];
#pragma unroll
    for (int i = 0; i < 16; i++) T[i >> 2][i & 3] = acc[12 + (i >> 2)][i & 3];
    nb_sync(NB_YZ, 160);
    TS(46);
#pragma unroll 1
    for (int bp = 5; bp >= 0; bp--) {
      uint32_t held[2];
#pragma unroll
      for (int o = 1; o >= 0; o--) {
#pragma unroll
        for (int k = 4; k >= 1; k--) mmac(T[k], qd[0][0], qd[0][1], qd[0][2], qd[0][3], F[16 * k + 1], F[16 * k], T[k - 1]);
        mmac(T[0], qd[0][0], qd[0][1], qd[0][2], qd[0][3], F[1], F[0], ci);
        ldsm4(qd[6], qp - 16 * 6);
        ldsm4(qd[7], qp - 16 * 7);
        sv = lds64(sta);
#pragma unroll
        for (int i = 1; i < 8; i++) {
#pragma unroll
          for (int k = 3; k >= 0; k--)
            mma(T[k][0], T[k][1], T[k][2], T[k][3], qd[i][0], qd[i][1], qd[i][2], qd[i][3], F[16 * k + 2 * i + 1], F[16 * k + 2 * i]);
          if (i < 7) ldsm4(qd[i - 1], qp - 128 - 16 * (i - 1));
          if (i == 2) {
            const uint32_t w0 = pack_bf(T[4][0], T[4][1]), w1 = pack_bf(T[4][2], T[4][3]);
            if (o) { held[0] = w0; held[1] = w1; }
            else st_x(yd, nz(w0), w1, held[0], held[1]);
          }
          if (i == 4) {
            if (2 * bp + o <= 4) sv = make_uint2(0, 0);
            ci[0] = bf_lo(sv.x); ci[1] = bf_hi(sv.x); ci[2] = bf_lo(sv.y); ci[3] = bf_hi(sv.y);
          }
        }
        qp -= 128; sta -= 256;
      }
      yd -= 32;
    }
#pragma unroll
    for (int B = 1; B >= 0; B--)
      st_x(ydst + B * 32, nz(pack_bf(T[2 * B][0], T[2 * B][1])), pack_bf(T[2 * B][2], T[2 * B][3]),
           pack_bf(T[2 * B + 1][0], T[2 * B + 1][1]), pack_bf(T[2 * B + 1][2], T[2 * B + 1][3]));
  }
}

__device__ __forceinline__ void dual_exp(const uint32_t* w, uint32_t* e) {
  const float L = 1.44268798828125f;
  uint32_t mx = bmax2(bmax2(w[0], w[1]), bmax2(w[2], w[3]));
  uint32_t mn = bmin2(bmin2(w[0], w[1]), bmin2(w[2], w[3]));
  mx = bmax2(mx, __shfl_xor_sync(0xffffffffu, mx, 1));
  mn = bmin2(mn, __shfl_xor_sync(0xffffffffu, mn, 1));
  mx = bmax2(mx, __shfl_xor_sync(0xffffffffu, mx, 2));
  mn = bmin2(mn, __shfl_xor_sync(0xffffffffu, mn, 2));
  const float mx0 = bf_lo(mx) * -L, mx1 = bf_hi(mx) * -L, mn0 = bf_lo(mn) * L, mn1 = bf_hi(mn) * L;
#pragma unroll
  for (int i = 0; i < 2; i++) {
    const float a0 = bf_lo(w[2 * i]), a1 = bf_hi(w[2 * i]), b0 = bf_lo(w[2 * i + 1]), b1 = bf_hi(w[2 * i + 1]);
    e[2 * i] = pack_bf(ex2(fmaf(a0, L, mx0)), ex2(fmaf(b0, L, mx0)));
    e[2 * i + 1] = pack_bf(ex2(fmaf(a1, L, mx1)), ex2(fmaf(b1, L, mx1)));
    e[4 + 2 * i] = pack_bf(ex2(fmaf(a0, -L, mn0)), ex2(fmaf(b0, -L, mn0)));
    e[5 + 2 * i] = pack_bf(ex2(fmaf(a1, -L, mn1)), ex2(fmaf(b1, -L, mn1)));
  }
}
__device__ __forceinline__ void normalise(uint32_t* e, const float (&s)[4]) {
  const uint32_t r = pack_bf(rcp(s[0]), rcp(s[2]));
  const __nv_bfloat162 rr = *(const __nv_bfloat162*)&r;
#pragma unroll
  for (int i = 0; i < 4; i++) {
    const __nv_bfloat162 v = __hmul2(*(const __nv_bfloat162*)&e[i], (i & 1) ? __high2bfloat162(rr) : __low2bfloat162(rr));
    e[i] = *(const uint32_t*)&v;
  }
}
__host__ __device__ constexpr uint64_t qdesc(uint32_t addr) { return mkdesc(addr, 128, 256, 0); }

__global__ void __launch_bounds__(NTHREADS, 1)
fused_kernel(const Params P, const __grid_constant__ CUtensorMap mx, const __grid_constant__ CUtensorMap mw,
             const __grid_constant__ CUtensorMap mo, const __grid_constant__ CUtensorMap mu,
             const __grid_constant__ CUtensorMap mout, const __grid_constant__ CUtensorMap mw4) {
  constexpr uint32_t sb = SB;
  const int tid = threadIdx.x, lane = tid & 31;
  const int warp = __shfl_sync(0xffffffffu, tid >> 5, 0);
  const int b = blockIdx.x, oct = b >> 3, i8 = b & 7;
  const int rt = oct < 8 ? oct : 15 - oct;
  const int hp = (oct >> 3) * 8 + i8;

  const int wg = warp >> 2, w = warp & 3;
  const int d = b * 4 + ((tid >> 5) & 3);
  if (tid < 384) {
    asm volatile("prefetch.tensormap [%0];" ::"l"(&mu) : "memory");
    asm volatile("prefetch.tensormap [%0];" ::"l"(&mw) : "memory");
    asm volatile("prefetch.tensormap [%0];" ::"l"(&mx) : "memory");
    asm volatile("prefetch.tensormap [%0];" ::"l"(&mw4) : "memory");
  }
  if (warp == 12) {
    if (lane == 0) {
#pragma unroll
      for (int i = 0; i < 9; i++) mbar_init(BAR(i), 1);
      asm volatile("fence.mbarrier_init.release.cluster;" ::: "memory");
    }
    __syncwarp();
    if (lane < 9) mbar_expect(BAR(0) + 8 * lane, lane == 5 ? 65536 : ((lane == 0 || lane > 5) ? 16384 : 28672));
    __syncwarp();
    e_tma3d(sb + OFF_W, &mw, BAR(MB_FULL), hp * 32, 0, 0);
    e_tma2d(sb + OFF_X + 3 * 16384, &mx, BAR(MB_FULL), 0, rt * 256);
  } else if (warp == 13) {
    if (lane == 0) {
#pragma unroll
      for (int i = 9; i < 39; i++) mbar_init(BAR(i), i < MB_EMPTY ? 1 : (i < MB_AUX ? 4 : 8));
      asm volatile("fence.mbarrier_init.release.cluster;" ::: "memory");
    }
    __syncwarp();
    if (lane < 9) mbar_expect(BAR(MB_FULL + 8) + 8 * lane, lane < 8 ? 16384 : 131072);
  }
  const KgenRaw raw = kgen_load(P, d, tid >> 7, lane);
  const unsigned short dsk = __ldg((const unsigned short*)P.Dskip + d);
  const uint32_t tb = sb + OFF_T + w * T_CH;
  const uint32_t kp = wg >= 2 ? sb + OFF_STG0 + 16384 + w * 2048 : ((tb + 127) & ~127u) + wg * 2048;
  const KgenAddr kad = kgen_addr(lane, wg == 3 ? sb + OFF_X + 32768 + w * 2048 : kp);
  if (warp == 12) {
#pragma unroll 1
    for (int kb = 1; kb < 4; kb++) {
      if (kb == U_AT) e_tma5d(sb + OFF_STG0, &mu, BAR(MB_URAW), i8 * 64, oct * 4);
      e_tma3d(sb + OFF_W + kb * 12288, &mw, BAR(MB_FULL) + 8 * kb, hp * 32, kb * 64, 0);
      e_tma2d(sb + OFF_X + (kb < 2 ? kb + 3 : kb - 2) * 16384, &mx, BAR(MB_FULL) + 8 * kb, kb * 64, rt * 256);
    }
    e_prefetch(P.x + (size_t)(rt * 256 + hp * 16) * 512, 16384);
    e_tma4d(sb + OFF_W + 4 * 12288, &mw4, BAR(MB_FULL + 4), hp * 32, 4);
    if (smem_u32(smem_raw) != SB) __trap();
    if (lane == 0) TS1(54);
  }
  float k[5][4], k2048, ksc;
  kgen_unit(raw, kad, blockIdx.y, k, k2048, ksc);
  TS(40 + wg);
  if ((fu(k[0][0]) & fu(k[1][0]) & fu(k[2][0]) & fu(k[3][0]) & fu(k[4][0])) == 0xffffffffu) sts32(kp, 0);
  if (wg == 3) {
    nb_sync(0, 512);
    if (warp == 12) {
      asm volatile("fence.proxy.async.shared::cta;" ::: "memory");
      e_tma2d(sb + OFF_X + 2 * 16384, &mx, BAR(MB_FULL + 4), 256, rt * 256);
    }
  } else if (wg) {
    nb_arrive(0, 512);
  }
  k2048 += __shfl_xor_sync(0xffffffffu, k2048, 16);
  k2048 += __shfl_xor_sync(0xffffffffu, k2048, 8);
  if (wg != 2) {
    uint32_t h[10];
#pragma unroll
    for (int j = 0; j < 10; j++) h[j] = hu(__floats2half2_rn(k[j >> 1][2 * (j & 1)], k[j >> 1][2 * (j & 1) + 1]));
    sts128(kp + lane * 16, h[0], h[1], h[2], h[3]);
    sts128(kp + 512 + lane * 16, h[4], h[5], h[6], h[7]);
    sts128(kp + 1024 + lane * 16, h[8], h[9], fu(k2048), fu(ksc));
  }
  if (wg == 0) { nb_arrive(NB_PREP, 512); nb_sync(0, 512); }
  else if (wg == 3) nb_arrive(NB_PREP, 512);
  else nb_sync(NB_PREP, 512);
  if (warp >= 12) {
    asm volatile("setmaxnreg.dec.sync.aligned.u32 32;");
    if (warp == 12) {
      uint32_t slot = sb + OFF_X + 3 * 16384;
#pragma unroll 1
      for (int n = 0; n < 11; n++) {
        mbar_spin(BAR(MB_EMPTY) + 8 * n);
        const int m = n + 5;
        e_tma2d(slot, &mx, BAR(MB_FULL) + 8 * m, (m & 7) * 64, rt * 256 + (m >> 3) * 128);
        slot = slot == sb + OFF_X + 4 * 16384 ? sb + OFF_X : slot + 16384;
        if (n == 7) e_prefetch(P.wo + (size_t)b * 2048, 4096);
      }
#pragma unroll 1
      for (int i = 0; i < 8; i++) {
        mbar_wait(BAR(MB_EMPTY + 10) + 8 * ((0x54332100u >> (4 * i)) & 7));
        const int w0 = (0x54736210u >> (4 * i)) & 7;
        e_tma3d(sb + OFF_W + w0 * 16384, &mo, BAR(MB_WO), 0, w0 * 64, (hp & 3) * 2);
      }
    } else {
      if (warp == 15) {
        const uint4 v0 = __ldg((const uint4*)P.wphi + hp * 64 + lane), v1 = __ldg((const uint4*)P.wphi + hp * 64 + 32 + lane);
        sts128(sb + OFF_PHI + (lane & 1) * 256 + (lane >> 1) * 16, v0.x, v0.y, v0.z, v0.w);
        sts128(sb + OFF_PHI + 512 + (lane & 1) * 256 + (lane >> 1) * 16, v1.x, v1.y, v1.z, v1.w);
        const uint32_t one = (((lane >> 3) ^ (lane >> 4)) & 1) ? 0u : ((lane & 1) ? 0x3F800000u : 0x3F80u);
        const int q = (lane >> 1) & 3;
        sts128(sb + OFF_EYE + lane * 16, q == 0 ? one : 0u, q == 1 ? one : 0u, q == 2 ? one : 0u, q == 3 ? one : 0u);
        sts64(sb + OFF_ONE + lane * 8, 0x3F803F80u, 0x3F803F80u);
        asm volatile("fence.proxy.async.shared::cta;" ::: "memory");
        nb_arrive(NB_KREAD, 160);
        mbar_wait(BAR(MB_EMPTY + ZERO_STEP));
        uint4* py = P.xs + X_Y + b * 1024 + lane;
#pragma unroll 1
        for (int i = 0; i < 1024; i += 32) st_x(py + i, 0, 0, 0, 0);
        nb_arrive(NB_YZ, 160);
        nb_arrive(NB_ODONE, 320);
        if (lane == 0) TS1(55);
        return;
      }
      uint32_t* const cnt = (uint32_t*)(P.xs + X_CNT) + (warp == 13 ? i8 : 8 + rt) * 32;
      const unsigned target = (ld_x32(cnt) & ~15u) + 16;
      if (warp == 13) {
        uint4* pp = P.xs + X_PART + (hp * 8 + rt) * 144 + lane;
#pragma unroll 1
        for (int i = 0; i < 144; i += 32) if (i + lane < 144) st_x(pp + i, 0, 0, 0, 0);
      }
      nb_sync(warp == 13 ? NB_INIT : NB_ODONE, warp == 13 ? 160 : 320);
      if (lane == 0) TS1(warp == 13 ? 49 : 56);
      asm volatile("fence.proxy.async.shared::cta;" ::: "memory");
      if (lane == 0) asm volatile("red.release.gpu.global.add.u32 [%0], 1;" ::"l"(cnt) : "memory");
      if (lane == 0) TS1(warp == 13 ? 50 : 57);
      const uint32_t* pc = (warp == 13 && (lane & 1)) ? (uint32_t*)(P.xs + X_CNT) + (b >> 4) * 32 : cnt;
#pragma unroll 1
      for (int i = 0; i < SPIN_MAX; i++) {
        unsigned v;
        asm volatile("ld.acquire.gpu.global.u32 %0, [%1];" : "=r"(v) : "l"(pc) : "memory");
        if (__all_sync(0xffffffffu, (int)(v - target) >= 0)) break;
      }
      if (lane == 0) TS1(warp == 13 ? 51 : 58);
      asm volatile("fence.proxy.async.global;" ::: "memory");
      if (warp == 13) {
        mbar_wait(BAR(MB_EMPTY + 11));
        e_expect(BAR(MB_UFULL), 4 * U_CH);
        e_bulk(sb + OFF_U, P.xs + X_UT + b * (U_CH / 4), 4 * U_CH, BAR(MB_UFULL));
      } else {
        const uint4* src = P.xs + X_O + (rt * 4 + (hp >> 2)) * 4096;
        e_expect(BAR(MB_OA), 14336);
        e_bulk(sb + OFF_STG0, src + 3200, 14336, BAR(MB_OA));
        e_expect(BAR(MB_OC), 32768);
        e_bulk(sb + OFF_X + 32768, src, 32768, BAR(MB_OC));
        nb_sync(NB_BDONE, 288);
        asm volatile("fence.proxy.async.shared::cta;" ::: "memory");
        e_expect(BAR(MB_OB), 18432);
        e_bulk(sb + OFF_U, src + 2048, 18432, BAR(MB_OB));
      }
    }
    return;
  }

  const int t = tid & 127;
  const int g = lane >> 2, c = lane & 3;
  {
    if (wg == 2) {
      asm volatile("setmaxnreg.inc.sync.aligned.u32 160;");
#pragma unroll
      for (int j = 0; j < 5; j++) { k[j][0] *= ksc; k[j][1] *= ksc; k[j][2] *= ksc; k[j][3] *= ksc; }
#pragma unroll 1
      for (int q = 0; q < 3; q++) {
        const uint32_t src = (q == 2 ? kp : ((tb + 127) & ~127u) + q * 2048) + lane * 16;
        const uint4 v0 = lds128(src), v1 = lds128(src + 512), v2 = lds128(src + 1024);
        const uint32_t h[10] = {v0.x, v0.y, v0.z, v0.w, v1.x, v1.y, v1.z, v1.w, v2.x, v2.y};
#pragma unroll
        for (int j = 0; j < 10; j++) {
          const float2 f = __half22float2(*(const __half2*)&h[j]);
          k[j >> 1][2 * (j & 1)] = fmaf(f.x, uf(v2.w), k[j >> 1][2 * (j & 1)]);
          k[j >> 1][2 * (j & 1) + 1] = fmaf(f.y, uf(v2.w), k[j >> 1][2 * (j & 1) + 1]);
        }
        k2048 += uf(v2.z);
      }
#pragma unroll
      for (int o2 = 4; o2; o2 >>= 1) k2048 += __shfl_xor_sync(0xffffffffu, k2048, o2);
      if (lane == 0) k[0][0] += bf_lo(dsk);
      __syncwarp();
      if (lane == 0) mbar_arrive(BAR(MB_AUX));
      TS(34);
      build_tables(tb, lane, k, k2048);
      TS(35);
      uint4* const g_y = P.xs + X_Y;
      conv_channel(sb + OFF_U + w * U_CH, tb, lane, g_y + (size_t)d * 256 + lane);
      nb_arrive(NB_BDONE, 288);
      TS(37);
      mbar_wait(BAR(MB_OA));
      const int lam = w * 8 + g;
      const uint4* src = g_y + (size_t)(oct * 32 + c * 8) * 256 + i8 * 32 + lam;
      uint4 v[8];
#pragma unroll 1
      for (int it = 0; it < SPIN_MAX; it++) {
        uint32_t m = 0xffffffffu;
#pragma unroll
        for (int i = 0; i < 8; i++) v[i] = ld_x(src + i * 256);
#pragma unroll
        for (int i = 0; i < 8; i++) m = min(m, v[i].x);
        if (__all_sync(0xffffffffu, m != 0)) break;
      }
      __nv_bfloat16* dst = P.out + (size_t)(i8 * 256 + (lam >> 2) * 16 + (lam & 3) * 2) * 1024 + 512 + oct * 32 + c * 8;
#pragma unroll
      for (int i = 0; i < 8; i++) *(uint4*)(dst + (size_t)((i >> 2) * 128 + ((i >> 1) & 1) * 8 + (i & 1)) * 1024) = tr_row(v, i);
      TS(38);
      GT(63);
      if (w == 0) TSDUMP(32);
      return;
    }
    if (wg == 1) {
      mbar_wait(BAR(MB_URAW));
      TS(48);
      uint4* dst = P.xs + X_UT + (i8 * 64 + g) * (U_CH / 16) + (c & 1) * (U_ODD / 16) + U_PAD / 16 + oct * 8 + w * 2 + (c >> 1);
      uint32_t r[8][4];
#pragma unroll
      for (int i = 0; i < 8; i++) ldsm4t(r[i], sb + OFF_STG0 + w * 4096 + lane * 128 + (((i ^ lane) & 7) << 4));
#pragma unroll
      for (int i = 0; i < 8; i++) dst[i * (U_CH / 2)] = make_uint4(r[i][0], r[i][1], r[i][2], r[i][3]);
      nb_arrive(NB_INIT, 160);
      if (lane == 0) mbar_arrive(BAR(MB_AUX));
      mbar_wait(BAR(MB_EMPTY + 4));
      mbar_spin(BAR(MB_EMPTY + 6));
    }
    TS(wg * 16 + 1);
  }

  float acc[2][48];
  {
    uint32_t fb = BAR(MB_FULL) + 64 * wg;
    uint32_t da = (uint32_t)mkdesc(sb + OFF_X, 16, 0, 0) + (wg ? 1024 : 3072), db = (uint32_t)mkdesc(sb + OFF_W, 4096, 0, 0);
    constexpr uint64_t ha = mkdesc(0, 0, 1024, 1), hb = mkdesc(0, 0, 512, 2);
    mbar_spin(fb);
    TS(wg * 16 + 2);
#pragma unroll 1
    for (int kb = 0; kb < 8; kb++) {
      WG_FENCE();
#pragma unroll
      for (int k = 0; k < 4; k++) {
        wgmma_ss_n96(acc[0], ha | (da + 2 * k), hb | (db + 64 * k), k ? 1 : kb);
        wgmma_ss_n96(acc[1], ha | (da + 2 * k + 512), hb | (db + 64 * k), k ? 1 : kb);
      }
      WG_COMMIT();
      if (kb < 7) mbar_spin(fb + 8);
      WG_WAIT(1);
      if (kb > 0) e_arrive(fb + 8 * (MB_EMPTY - MB_FULL - 1));
      fb += 8; db += 768;
      da = da == (uint32_t)mkdesc(sb + OFF_X + 65536, 16, 0, 0) ? da - 4096 : da + 1024;
    }
    if (wg == 0) nb_sync(NB_KREAD, 160);
    WG_WAIT(0);
    e_arrive(fb + 8 * (MB_EMPTY - MB_FULL - 1));
    mbar_spin(fb + 8 * (MB_EMPTY - MB_FULL - 1));
  }
  TS(wg * 16 + 3);
  asm volatile("setmaxnreg.inc.sync.aligned.u32 160;");

  constexpr uint32_t stg0 = sb + OFF_STG0, stg1 = sb + OFF_X + 32768;
  uint4* const g_part = P.xs + X_PART;
  uint4* const g_o = P.xs + X_O;
  constexpr uint32_t kvs = stg0;
  auto pack8 = [](const float* a) { return make_uint4(pack_bf(a[0], a[1]), pack_bf(a[2], a[3]), pack_bf(a[4], a[5]), pack_bf(a[6], a[7])); };
  auto feat = [&](const uint4 (&af)[4], float (&p)[4][8]) {
    WG_FENCE();
#pragma unroll
    for (int u = 0; u < 4; u++) wgmma_rs_n16(p[u], af[u], qdesc(sb + OFF_PHI + (u & 1) * 512), 0);
    WG_COMMIT();
  };
  auto packp = [](const float (&p)[4][8], uint32_t (&pw)[16]) {
#pragma unroll
    for (int i = 0; i < 16; i++) pw[i] = pack_bf(p[i >> 2][(i & 1) + 2 * (i & 2)], p[i >> 2][(i & 1) + 2 * (i & 2) + 2]);
  };
  auto contract = [&](float (&kc)[20], uint32_t stg, int acc_in) {
    WG_FENCE();
#pragma unroll
    for (int s = 0; s < 8; s++) wgmma_ss_n40(kc, qdesc(stg + s * SLAB), qdesc(stg + s * SLAB + 2048), s ? 1 : acc_in);
    WG_COMMIT();
    WG_WAIT(0);
  };
  uint32_t eq[32];
  {
    uint4 af[4], aq[4], vp[4];
    float p[4][8];
#pragma unroll
    for (int u = 0; u < 4; u++) af[u] = pack8(acc[u >> 1] + 16 + 8 * (u & 1));
    feat(af, p);
#pragma unroll
    for (int u = 0; u < 4; u++) { aq[u] = pack8(acc[u >> 1] + 8 * (u & 1)); vp[u] = pack8(acc[u >> 1] + 32 + 8 * (u & 1)); }
    WG_WAIT(0);
    uint32_t pw[16], ek[32];
    packp(p, pw);
#pragma unroll
    for (int u = 0; u < 4; u++) dual_exp(pw + 4 * u, ek + 8 * u);
    TS(wg * 16 + 12);
    float rs[8][4];
    WG_FENCE();
#pragma unroll
    for (int i = 0; i < 8; i++) wgmma_rs_n8(rs[i], make_uint4(ek[4 * i], ek[4 * i + 1], ek[4 * i + 2], ek[4 * i + 3]), qdesc(sb + OFF_ONE), 0);
    WG_COMMIT();
    feat(aq, p);
    WG_WAIT(0);
#pragma unroll
    for (int i = 0; i < 8; i++) normalise(ek + 4 * i, rs[i]);
    packp(p, pw);
    mbar_wait(BAR(MB_AUX));
    const uint32_t sl = (wg ? stg1 : stg0) + w * SLAB + lane * 16;
#pragma unroll
    for (int i = 0; i < 8; i++) stsm4(sl + (i >> 2) * 4 * SLAB + (i & 3) * 512, ek[4 * i], ek[4 * i + 1], ek[4 * i + 2], ek[4 * i + 3]);
#pragma unroll
    for (int i = 0; i < 4; i++) stsm4(sl + (i >> 1) * 4 * SLAB + 2048 + (i & 1) * 512, vp[i].x, vp[i].y, vp[i].z, vp[i].w);
    sts128(sl + (lane >> 4) * (4 * SLAB - 256) + 3072, 0x3F803F80u, 0x3F803F80u, 0x3F803F80u, 0x3F803F80u);
    asm volatile("fence.proxy.async.shared::cta;" ::: "memory");
    TS(wg * 16 + 13);
    if (wg) {
      nb_arrive(NB_ST0, 256);
    } else {
      float kc[20];
      uint4* pp = g_part + (size_t)(hp * 8 + rt) * 144 + t;
      uint32_t* pz = (uint32_t*)(pp - t + 128) + w * 16 + c * 8 + g;
      asm volatile("" : "+l"(pp), "+l"(pz));
      nb_sync(NB_WG0, 128);
      contract(kc, stg0, 0);
      mbar_wait(BAR(MB_UFULL));
      TS(15);
      nb_sync(NB_ST0, 256);
      contract(kc, stg1, 1);
      TS(6);
      float kv[8];
#pragma unroll
      for (int i = 0; i < 8; i++) kv[i] = w & 2 ? kc[8 + i] : kc[i];
      st_x(pp, nz(pack_bf(kv[0], kv[1])), pack_bf(kv[2], kv[3]), pack_bf(kv[4], kv[5]), pack_bf(kv[6], kv[7]));
      if (c < 2) st_x32(pz, nz(fu(c ? kc[18] : kc[16])));
      TS(5);
    }
#pragma unroll
    for (int u = 0; u < 4; u++) dual_exp(pw + 4 * u, eq + 8 * u);
  }
  TS(wg * 16 + 4);
  if (wg == 1) {
    mbar_wait(BAR(MB_UFULL));
    const uint4* ps = g_part + (size_t)hp * 8 * 144 + t;
    const uint32_t* zs = (const uint32_t*)(g_part + (size_t)(hp * 8 + (lane >> 4) * 4) * 144 + 128) + w * 16 + (lane & 15);
    uint4 v[8];
    uint32_t zv[4];
#pragma unroll 1
    for (int it = 0; it < SPIN_MAX; it++) {
#pragma unroll
      for (int i = 0; i < 8; i++) v[i] = ld_x(ps + i * 144);
#pragma unroll
      for (int i = 0; i < 4; i++) zv[i] = ld_x32(zs + i * 576);
      uint32_t m = min(min(zv[0], zv[1]), min(zv[2], zv[3]));
#pragma unroll
      for (int i = 0; i < 8; i++) m = min(m, v[i].x);
      if (__all_sync(0xffffffffu, m != 0)) break;
    }
    float s[8];
    WG_FENCE();
#pragma unroll
    for (int r = 0; r < 8; r++) wgmma_rs_n16(s, v[r], qdesc(sb + OFF_EYE), r);
    WG_COMMIT();
    float zsum = (uf(zv[0]) + uf(zv[1])) + (uf(zv[2]) + uf(zv[3]));
    zsum += __shfl_xor_sync(0xffffffffu, zsum, 16);
    const uint32_t z1 = pack_bf(zsum, 1.f);
    if (lane < 16) sts128(kvs + w * 768 + 512 + lane * 16, z1, z1, z1, z1);
    WG_WAIT(0);
    stsm4(kvs + w * 768 + lane * 16, pack_bf(s[0], s[1]), pack_bf(s[2], s[3]), pack_bf(s[4], s[5]), pack_bf(s[6], s[7]));
    asm volatile("fence.proxy.async.shared::cta;" ::: "memory");
    TS(22);
  }
  nb_sync(NB_KV, 256);
  {
    float n[8][12];
    WG_FENCE();
#pragma unroll
    for (int i = 0; i < 8; i++) wgmma_rs_n24(n[i], make_uint4(eq[4 * i], eq[4 * i + 1], eq[4 * i + 2], eq[4 * i + 3]), qdesc(kvs + (i & 3) * 768), 0);
    WG_COMMIT();
    uint32_t* od = (uint32_t*)(g_o + (size_t)((rt * 4 + wg * 2) * 32 + hp * 2) * 128) + w * 64 + lane;
    WG_WAIT(0);
#pragma unroll
    for (int u = 0; u < 4; u++) {
      float(&np)[12] = n[2 * u];
      const float(&nm)[12] = n[2 * u + 1];
      const float q0 = np[9] * rcp(nm[9]), q1 = np[11] * rcp(nm[11]);
      const float r0 = rcp(fmaf(nm[8], q0, fmaf(np[9], 1e-6f, np[8]))), r1 = rcp(fmaf(nm[10], q1, fmaf(np[11], 1e-6f, np[10])));
#pragma unroll
      for (int i = 0; i < 8; i++) np[i] = fmaf(nm[i], (i & 2) ? q1 : q0, np[i]);
      uint32_t* o = od + (u >> 1) * 16384 + (u & 1) * 512;
      o[0] = pack_bf(np[0] * r0, np[1] * r0);
      o[32] = pack_bf(np[2] * r1, np[3] * r1);
      o[256] = pack_bf(np[4] * r0, np[5] * r0);
      o[288] = pack_bf(np[6] * r1, np[7] * r1);
    }
  }
  TS(wg * 16 + 7);
  nb_arrive(NB_ODONE, 320);
  if (wg) { if (w == 0) TSDUMP(16); return; }
  mbar_wait(BAR(MB_WO));
  mbar_wait(BAR(MB_OA));
  TS(8);
  nb_sync(NB_BDONE, 288);
  TS(9);
  float oc[64];
  {
    constexpr uint64_t ha = mkdesc(0, 0, 128, 0), hb = mkdesc(0, 0, 1024, 1);
    constexpr uint32_t da0 = (uint32_t)mkdesc(stg1, 1024, 0, 0), db0 = (uint32_t)mkdesc(sb + OFF_W, 8192, 0, 0);
#pragma unroll 1
    for (int j = 0; j < 8; j++) {
      const int kb = (j + 7) & 7;
      if ((j & 3) == 1) mbar_spin(j == 1 ? BAR(MB_OC) : BAR(MB_OB));
      WG_FENCE();
#pragma unroll
      for (int k = 0; k < 4; k++) wgmma_ss_n128(oc, ha | (da0 + 512 * kb + 128 * k), hb | (db0 + 1024 * kb + 128 * k), k ? 1 : j);
      WG_COMMIT();
    }
    WG_WAIT(0);
  }
  TS(10);
  nb_sync(NB_WG0, 128);
  const uint32_t ot = sb + OFF_W + w * 4096;
#pragma unroll
  for (int i = 0; i < 16; i += 2)
    stsm4(ot + (i >> 3) * 2048 + (lane & 15) * 128 + (((i + (lane >> 4)) ^ lane) & 7) * 16, pack_bf(oc[4 * i], oc[4 * i + 1]),
          pack_bf(oc[4 * i + 2], oc[4 * i + 3]), pack_bf(oc[4 * i + 4], oc[4 * i + 5]), pack_bf(oc[4 * i + 6], oc[4 * i + 7]));
  asm volatile("fence.proxy.async.shared::cta;" ::: "memory");
  __syncwarp();
  e_store3d(&mout, ot, (rt * 4 + (hp >> 2)) * 64 + w * 16, (hp & 3) * 2);
  TS(wg * 16 + 11);
  GT(61 + wg);
  if (w == 0) TSDUMP(0);
  if (w == 1) TSDUMP(48);
}

typedef CUresult (*EncodeFn)(CUtensorMap*, CUtensorMapDataType, cuuint32_t, void*, const cuuint64_t*, const cuuint64_t*,
                             const cuuint32_t*, const cuuint32_t*, CUtensorMapInterleave, CUtensorMapSwizzle,
                             CUtensorMapL2promotion, CUtensorMapFloatOOBfill);

}

extern "C" void kernel_launch(void* const* d_in, const int* in_sizes, int n_in, void* d_out, int out_size) {
  (void)in_sizes; (void)n_in; (void)out_size;
  void* fn = nullptr;
  cudaDriverEntryPointQueryResult qr;
  cudaGetDriverEntryPoint("cuTensorMapEncodeTiled", &fn, cudaEnableDefault, &qr);
  EncodeFn enc = (EncodeFn)fn;
  CUtensorMap mx, mw, mo, mu, mout, mw4;
  const cuuint32_t es[5] = {1, 1, 1, 1, 1};
  {
    cuuint64_t dims[2] = {512, 2048}, st[1] = {1024};
    cuuint32_t box[2] = {64, 128};
    enc(&mx, CU_TENSOR_MAP_DATA_TYPE_BFLOAT16, 2, d_in[0], dims, st, box, es, CU_TENSOR_MAP_INTERLEAVE_NONE,
        CU_TENSOR_MAP_SWIZZLE_128B, CU_TENSOR_MAP_L2_PROMOTION_L2_128B, CU_TENSOR_MAP_FLOAT_OOB_FILL_NONE);
  }
  {
    cuuint64_t dims[3] = {512, 512, 3}, st[2] = {3072, 1024};
    cuuint32_t box[3] = {32, 64, 3};
    enc(&mw, CU_TENSOR_MAP_DATA_TYPE_BFLOAT16, 3, d_in[1], dims, st, box, es, CU_TENSOR_MAP_INTERLEAVE_NONE,
        CU_TENSOR_MAP_SWIZZLE_64B, CU_TENSOR_MAP_L2_PROMOTION_L2_128B, CU_TENSOR_MAP_FLOAT_OOB_FILL_NONE);
  }
  {
    cuuint64_t dims[3] = {64, 512, 8}, st[2] = {1024, 128};
    cuuint32_t box[3] = {64, 64, 2};
    enc(&mo, CU_TENSOR_MAP_DATA_TYPE_BFLOAT16, 3, d_in[3], dims, st, box, es, CU_TENSOR_MAP_INTERLEAVE_NONE,
        CU_TENSOR_MAP_SWIZZLE_128B, CU_TENSOR_MAP_L2_PROMOTION_L2_128B, CU_TENSOR_MAP_FLOAT_OOB_FILL_NONE);
  }
  {
    cuuint64_t dims[5] = {512, 2, 4, 4, 64}, st[4] = {1024, 8192, 2048, 32768};
    cuuint32_t box[5] = {64, 2, 4, 4, 4};
    enc(&mu, CU_TENSOR_MAP_DATA_TYPE_BFLOAT16, 5, d_in[4], dims, st, box, es, CU_TENSOR_MAP_INTERLEAVE_NONE,
        CU_TENSOR_MAP_SWIZZLE_128B, CU_TENSOR_MAP_L2_PROMOTION_L2_128B, CU_TENSOR_MAP_FLOAT_OOB_FILL_NONE);
  }
  {
    cuuint64_t dims[3] = {64, 2048, 16}, st[2] = {2048, 128};
    cuuint32_t box[3] = {64, 16, 2};
    enc(&mout, CU_TENSOR_MAP_DATA_TYPE_BFLOAT16, 3, d_out, dims, st, box, es, CU_TENSOR_MAP_INTERLEAVE_NONE,
        CU_TENSOR_MAP_SWIZZLE_128B, CU_TENSOR_MAP_L2_PROMOTION_NONE, CU_TENSOR_MAP_FLOAT_OOB_FILL_NONE);
  }
  {
    cuuint64_t dims[4] = {512, 64, 3, 8}, st[3] = {3072, 1024, 64 * 3072};
    cuuint32_t box[4] = {32, 64, 3, 4};
    enc(&mw4, CU_TENSOR_MAP_DATA_TYPE_BFLOAT16, 4, d_in[1], dims, st, box, es, CU_TENSOR_MAP_INTERLEAVE_NONE,
        CU_TENSOR_MAP_SWIZZLE_64B, CU_TENSOR_MAP_L2_PROMOTION_L2_128B, CU_TENSOR_MAP_FLOAT_OOB_FILL_NONE);
  }
  Params P;
  P.x = (const __nv_bfloat16*)d_in[0];
  P.wphi = (const __nv_bfloat16*)d_in[2];
  P.wo = (const __nv_bfloat16*)d_in[3];
  P.logA = (const __nv_bfloat16*)d_in[5];
  P.Aim = (const __nv_bfloat16*)d_in[6];
  P.Cre = (const __nv_bfloat16*)d_in[7];
  P.Cim = (const __nv_bfloat16*)d_in[8];
  P.logdt = (const __nv_bfloat16*)d_in[9];
  P.Dskip = (const __nv_bfloat16*)d_in[10];
  P.out = (__nv_bfloat16*)d_out;
  cudaGetSymbolAddress((void**)&P.xs, g_x);
  P.ts = nullptr;
  cudaFuncSetAttribute(fused_kernel, cudaFuncAttributeMaxDynamicSharedMemorySize, SMEM_BYTES);
  fused_kernel<<<NCTA, NTHREADS, SMEM_BYTES>>>(P, mx, mw, mo, mu, mout, mw4);
}
```

```cpp
#include <cuda_runtime.h>
#include <cuda_bf16.h>
#include <cuda_fp16.h>
#include <cuda.h>
#include <stdint.h>

#define DBG_TS 0

namespace {

constexpr int NTHREADS = 512;
constexpr int NCTA = 128;
constexpr int OFF_W = 0;
constexpr int OFF_X = 98304;
constexpr int OFF_U = OFF_X + 65536;
constexpr int U_CH = 4416, U_ODD = 2240, U_PAD = 128;
constexpr int OFF_STG0 = OFF_U + 18432;
constexpr int SLAB = 3328;
constexpr int OFF_T = OFF_STG0 + 8 * SLAB;
constexpr int T_CH = 5216;
constexpr int T_D = 0;
constexpr int T_5 = 2144;
constexpr int T_3 = T_5 + 384;
constexpr int T_7 = T_5 + 1024;
constexpr int T_9 = T_7 + 320;
constexpr int T_KC = T_9 + 320;
constexpr int T_ST = T_5 - 1024;
constexpr int OFF_PHI = OFF_T + 4 * T_CH;
constexpr int OFF_EYE = OFF_PHI + 1024, OFF_ONE = OFF_EYE + 512;
constexpr int OFF_BAR = OFF_ONE + 256;
constexpr int SMEM_BYTES = OFF_BAR + 512 + 256 * DBG_TS;
constexpr uint32_t SB = 1024;
static_assert(T_KC + 2 * 656 <= T_CH, "table size");
static_assert(SMEM_BYTES <= 232448, "smem");
constexpr int MB_URAW = 0, MB_FULL = 1  , MB_WO = 17, MB_UFULL = 18, MB_OA = 19, MB_OB = 20, MB_OC = 21,
              MB_EMPTY = 22  , MB_AUX = 38;
__host__ __device__ constexpr uint32_t BAR(int i) { return SB + OFF_BAR + 8 * i; }
constexpr int NB_WG0 = 1, NB_ODONE = 2, NB_ST0 = 3  , NB_KV = 5, NB_YZ = 6, NB_INIT = 7, NB_PREP = 8, NB_PROD = 9, NB_KREAD = 10, NB_BDONE = 11, NB_ZERO = 12;
#define U_AT 2
#define ZERO_STEP 15
constexpr int SPIN_MAX = 1 << 16;

constexpr int X_CNT = 0;
constexpr int X_PART = 128;
constexpr int X_O = X_PART + 16 * 8 * 144;
constexpr int X_Y = X_O + 32 * 32 * 128;
constexpr int X_UT = X_Y + 512 * 8 * 32;
constexpr int X_SIZE = X_UT + 512 * (U_CH / 16);
__device__ __align__(128) uint4 g_x[X_SIZE];
extern __shared__ uint8_t smem_raw[];
#define TS(i) do {} while (0)
#define TS1(i) do {} while (0)
#define GT(i) do {} while (0)
#define TSDUMP(base) do {} while (0)

__device__ __forceinline__ uint32_t smem_u32(const void* p) { return (uint32_t)__cvta_generic_to_shared(p); }
__device__ __forceinline__ void mbar_arrive(uint32_t b) {
  asm volatile("mbarrier.arrive.shared::cta.b64 _, [%0];" ::"r"(b) : "memory");
}
__device__ __forceinline__ void mbar_wait(uint32_t b) {
  uint32_t done = 0;
#pragma unroll 1
  for (int i = 0; i < SPIN_MAX && !done; i++) {
    asm volatile("{\n.reg .pred p;\nmbarrier.try_wait.parity.shared::cta.b64 p, [%1], 0, 4000;\nselp.u32 %0, 1, 0, p;\n}\n"
                 : "=r"(done) : "r"(b) : "memory");
  }
}
__device__ __forceinline__ void mbar_spin(uint32_t b) {
  uint32_t done = 0;
#pragma unroll 1
  for (int i = 0; i < (SPIN_MAX << 4) && !done; i++) {
    asm volatile("{\n.reg .pred p;\nmbarrier.try_wait.parity.shared::cta.b64 p, [%1], 0;\nselp.u32 %0, 1, 0, p;\n}\n"
                 : "=r"(done) : "r"(b) : "memory");
  }
}
__device__ __forceinline__ void mbar_init(uint32_t b, int n) {
  asm volatile("mbarrier.init.shared::cta.b64 [%0], %1;" ::"r"(b), "r"(n) : "memory");
}
__device__ __forceinline__ void mbar_expect(uint32_t b, int bytes) {
  asm volatile("mbarrier.arrive.expect_tx.shared::cta.b64 _, [%0], %1;" ::"r"(b), "r"(bytes) : "memory");
}
__device__ __forceinline__ void nb_sync(int id, int n) { asm volatile("bar.sync %0, %1;" ::"r"(id), "r"(n) : "memory"); }
__device__ __forceinline__ void nb_arrive(int id, int n) { asm volatile("bar.arrive %0, %1;" ::"r"(id), "r"(n) : "memory"); }
#define ELECT "{\n.reg .pred p;\nelect.sync _|p, 0xffffffff;\n@p "
__device__ __forceinline__ void e_arrive(uint32_t b) {
  asm volatile(ELECT "mbarrier.arrive.shared::cta.b64 _, [%0];\n}\n" ::"r"(b) : "memory");
}
__device__ __forceinline__ void e_expect(uint32_t b, int bytes) {
  asm volatile(ELECT "mbarrier.arrive.expect_tx.shared::cta.b64 _, [%0], %1;\n}\n" ::"r"(b), "r"(bytes) : "memory");
}
__device__ __forceinline__ void e_tma2d(uint32_t dst, const CUtensorMap* m, uint32_t bar, int c0, int c1) {
  asm volatile(ELECT "cp.async.bulk.tensor.2d.shared::cluster.global.mbarrier::complete_tx::bytes [%0], [%1, {%3,%4}], [%2];\n}\n"
               ::"r"(dst), "l"(m), "r"(bar), "r"(c0), "r"(c1) : "memory");
}
__device__ __forceinline__ void e_tma3d(uint32_t dst, const CUtensorMap* m, uint32_t bar, int c0, int c1, int c2) {
  asm volatile(ELECT "cp.async.bulk.tensor.3d.shared::cluster.global.mbarrier::complete_tx::bytes [%0], [%1, {%3,%4,%5}], [%2];\n}\n"
               ::"r"(dst), "l"(m), "r"(bar), "r"(c0), "r"(c1), "r"(c2) : "memory");
}
__device__ __forceinline__ void e_tma4d(uint32_t dst, const CUtensorMap* m, uint32_t bar, int c0, int c3) {
  asm volatile(ELECT "cp.async.bulk.tensor.4d.shared::cluster.global.mbarrier::complete_tx::bytes [%0], [%1, {%3,%5,%5,%4}], [%2];\n}\n"
               ::"r"(dst), "l"(m), "r"(bar), "r"(c0), "r"(c3), "r"(0) : "memory");
}
__device__ __forceinline__ void e_bulk(uint32_t dst, const void* src, int bytes, uint32_t bar) {
  asm volatile(ELECT "cp.async.bulk.shared::cluster.global.mbarrier::complete_tx::bytes [%0], [%1], %2, [%3];\n}\n"
               ::"r"(dst), "l"(src), "r"(bytes), "r"(bar) : "memory");
}
__device__ __forceinline__ void e_prefetch(const void* p, int bytes) {
  asm volatile(ELECT "cp.async.bulk.prefetch.L2.global [%0], %1;\n}\n" ::"l"(p), "r"(bytes) : "memory");
}
__device__ __forceinline__ void e_store3d(const CUtensorMap* m, uint32_t src, int c1, int c2) {
  asm volatile(ELECT "cp.async.bulk.tensor.3d.global.shared::cta.bulk_group [%0, {%4,%2,%3}], [%1];\n"
               "@p cp.async.bulk.commit_group;\n@p cp.async.bulk.wait_group.read 0;\n}\n"
               ::"l"(m), "r"(src), "r"(c1), "r"(c2), "r"(0) : "memory");
}
__host__ __device__ constexpr uint64_t mkdesc(uint32_t addr, uint32_t lbo, uint32_t sbo, int swz) {
  return (uint64_t)((addr & 0x3FFFF) >> 4) | ((uint64_t)(lbo >> 4) << 16) | ((uint64_t)(sbo >> 4) << 32) |
         ((uint64_t)swz << 62);
}
#define WG_FENCE() asm volatile("wgmma.fence.sync.aligned;" ::: "memory")
#define WG_COMMIT() asm volatile("wgmma.commit_group.sync.aligned;" ::: "memory")
#define WG_WAIT(n) asm volatile("wgmma.wait_group.sync.aligned " #n ";" ::: "memory")

__device__ __forceinline__ void mma(float& d0, float& d1, float& d2, float& d3, uint32_t a0, uint32_t a1, uint32_t a2,
                                    uint32_t a3, uint32_t b0, uint32_t b1) {
  asm volatile("mma.sync.aligned.m16n8k16.row.col.f32.bf16.bf16.f32 {%0,%1,%2,%3},{%4,%5,%6,%7},{%8,%9},{%0,%1,%2,%3};"
               : "+f"(d0), "+f"(d1), "+f"(d2), "+f"(d3)
               : "r"(a0), "r"(a1), "r"(a2), "r"(a3), "r"(b0), "r"(b1));
}
__device__ __forceinline__ void mmac(float (&d)[4], uint32_t a0, uint32_t a1, uint32_t a2, uint32_t a3, uint32_t b0,
                                     uint32_t b1, const float (&c)[4]) {
  asm volatile("mma.sync.aligned.m16n8k16.row.col.f32.bf16.bf16.f32 {%0,%1,%2,%3},{%4,%5,%6,%7},{%8,%9},{%10,%11,%12,%13};"
               : "=f"(d[0]), "=f"(d[1]), "=f"(d[2]), "=f"(d[3])
               : "r"(a0), "r"(a1), "r"(a2), "r"(a3), "r"(b0), "r"(b1), "f"(c[0]), "f"(c[1]), "f"(c[2]), "f"(c[3]));
}
__device__ __forceinline__ void mma_p(int p, float (&d)[4], uint32_t a0, uint32_t a1, uint32_t a2, uint32_t a3, uint32_t b0, uint32_t b1) {
  asm volatile("{\n.reg .pred q;\nsetp.ne.b32 q, %10, 0;\n"
               "@q mma.sync.aligned.m16n8k16.row.col.f32.bf16.bf16.f32 {%0,%1,%2,%3},{%4,%5,%6,%7},{%8,%9},{%0,%1,%2,%3};\n}\n"
               : "+f"(d[0]), "+f"(d[1]), "+f"(d[2]), "+f"(d[3])
               : "r"(a0), "r"(a1), "r"(a2), "r"(a3), "r"(b0), "r"(b1), "r"(p));
}
__device__ __forceinline__ void mmac_p(int p, float (&d)[4], uint32_t a0, uint32_t a1, uint32_t a2, uint32_t a3, uint32_t b0,
                                       uint32_t b1, const float (&c)[4]) {
  asm volatile("{\n.reg .pred q;\nsetp.ne.b32 q, %14, 0;\n"
               "@q mma.sync.aligned.m16n8k16.row.col.f32.bf16.bf16.f32 {%0,%1,%2,%3},{%4,%5,%6,%7},{%8,%9},{%10,%11,%12,%13};\n}\n"
               : "+f"(d[0]), "+f"(d[1]), "+f"(d[2]), "+f"(d[3])
               : "r"(a0), "r"(a1), "r"(a2), "r"(a3), "r"(b0), "r"(b1), "f"(c[0]), "f"(c[1]), "f"(c[2]), "f"(c[3]), "r"(p));
}
__device__ __forceinline__ void mma_h(float (&d)[4], const uint32_t (&a)[4], uint32_t b0, uint32_t b1) {
  asm volatile("mma.sync.aligned.m16n8k16.row.col.f32.f16.f16.f32 {%0,%1,%2,%3},{%4,%5,%6,%7},{%8,%9},{%0,%1,%2,%3};"
               : "+f"(d[0]), "+f"(d[1]), "+f"(d[2]), "+f"(d[3]) : "r"(a[0]), "r"(a[1]), "r"(a[2]), "r"(a[3]), "r"(b0), "r"(b1));
}
__device__ __forceinline__ void mma0(float& d0, float& d1, float& d2, float& d3, uint32_t a0, uint32_t a1, uint32_t a2,
                                     uint32_t a3, uint32_t b0, uint32_t b1) {
  asm volatile("mma.sync.aligned.m16n8k16.row.col.f32.bf16.bf16.f32 {%0,%1,%2,%3},{%4,%5,%6,%7},{%8,%9},{%10,%10,%10,%10};"
               : "=f"(d0), "=f"(d1), "=f"(d2), "=f"(d3)
               : "r"(a0), "r"(a1), "r"(a2), "r"(a3), "r"(b0), "r"(b1), "f"(0.f));
}
__device__ __forceinline__ uint32_t pack_bf(float lo, float hi) {
  uint32_t r;
  asm("cvt.rn.bf16x2.f32 %0, %1, %2;" : "=r"(r) : "f"(hi), "f"(lo));
  return r;
}
__device__ __forceinline__ float bf_lo(uint32_t w) { return __uint_as_float(w << 16); }
__device__ __forceinline__ float bf_hi(uint32_t w) { return __uint_as_float(w & 0xffff0000u); }
__device__ __forceinline__ float bf_round(float x) { return __bfloat162float(__float2bfloat16_rn(x)); }
__device__ __forceinline__ uint32_t bmax2(uint32_t a, uint32_t b) {
  uint32_t r; asm("max.bf16x2 %0, %1, %2;" : "=r"(r) : "r"(a), "r"(b)); return r;
}
__device__ __forceinline__ uint32_t bmin2(uint32_t a, uint32_t b) {
  uint32_t r; asm("min.bf16x2 %0, %1, %2;" : "=r"(r) : "r"(a), "r"(b)); return r;
}
__device__ __forceinline__ float ex2(float x) { float r; asm("ex2.approx.ftz.f32 %0, %1;" : "=f"(r) : "f"(x)); return r; }
__device__ __forceinline__ float rcp(float x) { float r; asm("rcp.approx.ftz.f32 %0, %1;" : "=f"(r) : "f"(x)); return r; }
__device__ __forceinline__ void ldsm4(uint32_t (&r)[4], uint32_t a) {
  asm volatile("ldmatrix.sync.aligned.m8n8.x4.shared.b16 {%0,%1,%2,%3}, [%4];"
               : "=r"(r[0]), "=r"(r[1]), "=r"(r[2]), "=r"(r[3]) : "r"(a) : "memory");
}
__device__ __forceinline__ void ldsm4t(uint32_t (&r)[4], uint32_t a) {
  asm volatile("ldmatrix.sync.aligned.m8n8.x4.trans.shared.b16 {%0,%1,%2,%3}, [%4];"
               : "=r"(r[0]), "=r"(r[1]), "=r"(r[2]), "=r"(r[3]) : "r"(a) : "memory");
}
__device__ __forceinline__ void stsm4(uint32_t a, uint32_t r0, uint32_t r1, uint32_t r2, uint32_t r3) {
  asm volatile("stmatrix.sync.aligned.m8n8.x4.shared.b16 [%0], {%1,%2,%3,%4};"
               ::"r"(a), "r"(r0), "r"(r1), "r"(r2), "r"(r3) : "memory");
}
__device__ __forceinline__ uint32_t lds32(uint32_t a) {
  uint32_t r; asm volatile("ld.shared.u32 %0, [%1];" : "=r"(r) : "r"(a) : "memory"); return r;
}
__device__ __forceinline__ uint32_t lds16(uint32_t a) {
  uint32_t r; asm volatile("{\n.reg .u16 h;\nld.shared.u16 h, [%1];\ncvt.u32.u16 %0, h;\n}\n" : "=r"(r) : "r"(a) : "memory"); return r;
}
__device__ __forceinline__ uint2 lds64(uint32_t a) {
  uint2 r; asm volatile("ld.shared.v2.u32 {%0,%1}, [%2];" : "=r"(r.x), "=r"(r.y) : "r"(a) : "memory"); return r;
}
__device__ __forceinline__ uint4 lds128(uint32_t a) {
  uint4 r;
  asm volatile("ld.shared.v4.u32 {%0,%1,%2,%3}, [%4];" : "=r"(r.x), "=r"(r.y), "=r"(r.z), "=r"(r.w) : "r"(a) : "memory");
  return r;
}
__device__ __forceinline__ void sts32(uint32_t a, uint32_t v) { asm volatile("st.shared.u32 [%0], %1;" ::"r"(a), "r"(v) : "memory"); }
__device__ __forceinline__ void sts16(uint32_t a, uint32_t v) {
  asm volatile("{\n.reg .u16 h;\ncvt.u16.u32 h, %1;\nst.shared.u16 [%0], h;\n}\n" ::"r"(a), "r"(v) : "memory");
}
__device__ __forceinline__ void sts64(uint32_t a, uint32_t x, uint32_t y) {
  asm volatile("st.shared.v2.u32 [%0], {%1,%2};" ::"r"(a), "r"(x), "r"(y) : "memory");
}
__device__ __forceinline__ void sts128(uint32_t a, uint32_t x, uint32_t y, uint32_t z, uint32_t w) {
  asm volatile("st.shared.v4.u32 [%0], {%1,%2,%3,%4};" ::"r"(a), "r"(x), "r"(y), "r"(z), "r"(w) : "memory");
}
__device__ __forceinline__ uint4 ld_x(const uint4* p) {
  uint4 r;
  asm volatile("{\n.reg .b128 t;\nld.relaxed.gpu.global.b128 t, [%4];\nmov.b128 {%0,%1,%2,%3}, t;\n}\n"
               : "=r"(r.x), "=r"(r.y), "=r"(r.z), "=r"(r.w) : "l"(p) : "memory");
  return r;
}
__device__ __forceinline__ uint32_t ld_x32(const uint32_t* p) {
  uint32_t r; asm volatile("ld.relaxed.gpu.global.u32 %0, [%1];" : "=r"(r) : "l"(p) : "memory"); return r;
}
__device__ __forceinline__ void st_x(uint4* p, uint32_t x, uint32_t y, uint32_t z, uint32_t w) {
  asm volatile("{\n.reg .b128 t;\nmov.b128 t, {%1,%2,%3,%4};\nst.relaxed.gpu.global.b128 [%0], t;\n}\n"
               ::"l"(p), "r"(x), "r"(y), "r"(z), "r"(w) : "memory");
}
__device__ __forceinline__ void st_x_p(int p, uint4* a, uint32_t x, uint32_t y, uint32_t z, uint32_t w) {
  asm volatile("{\n.reg .b128 t;\n.reg .pred q;\nsetp.ne.b32 q, %5, 0;\nmov.b128 t, {%1,%2,%3,%4};\n@q st.relaxed.gpu.global.b128 [%0], t;\n}\n"
               ::"l"(a), "r"(x), "r"(y), "r"(z), "r"(w), "r"(p) : "memory");
}
__device__ __forceinline__ void sts64_p(int p, uint32_t a, uint32_t x, uint32_t y) {
  asm volatile("{\n.reg .pred q;\nsetp.ne.b32 q, %3, 0;\n@q st.shared.v2.u32 [%0], {%1,%2};\n}\n" ::"r"(a), "r"(x), "r"(y), "r"(p) : "memory");
}
__device__ __forceinline__ void st_x32(uint32_t* p, uint32_t x) {
  asm volatile("st.relaxed.gpu.global.u32 [%0], %1;" ::"l"(p), "r"(x) : "memory");
}
__device__ __forceinline__ uint32_t nz(uint32_t w) { return max(w, 1u); }
__device__ __forceinline__ uint32_t fu(float x) { return __float_as_uint(x); }
__device__ __forceinline__ float uf(uint32_t x) { return __uint_as_float(x); }

__device__ __forceinline__ void wgmma_ss_n96(float (&d)[48], uint64_t da, uint64_t db, int sc) {
  asm volatile("{\n.reg .pred p;\nsetp.ne.b32 p, %50, 0;\n"
      "wgmma.mma_async.sync.aligned.m64n96k16.f32.bf16.bf16 "
      "{%0,%1,%2,%3,%4,%5,%6,%7,%8,%9,%10,%11,%12,%13,%14,%15,%16,%17,%18,%19,%20,%21,%22,%23,%24,%25,%26,%27,%28,%29,%30,%31,%32,%33,%34,%35,%36,%37,%38,%39,%40,%41,%42,%43,%44,%45,%46,%47}, "
      "%48, %49, p, 1, 1, 0, 1;\n}\n"
      : "+f"(d[0]), "+f"(d[1]), "+f"(d[2]), "+f"(d[3]), "+f"(d[4]), "+f"(d[5]), "+f"(d[6]), "+f"(d[7]),
        "+f"(d[8]), "+f"(d[9]), "+f"(d[10]), "+f"(d[11]), "+f"(d[12]), "+f"(d[13]), "+f"(d[14]), "+f"(d[15]),
        "+f"(d[16]), "+f"(d[17]), "+f"(d[18]), "+f"(d[19]), "+f"(d[20]), "+f"(d[21]), "+f"(d[22]), "+f"(d[23]),
        "+f"(d[24]), "+f"(d[25]), "+f"(d[26]), "+f"(d[27]), "+f"(d[28]), "+f"(d[29]), "+f"(d[30]), "+f"(d[31]),
        "+f"(d[32]), "+f"(d[33]), "+f"(d[34]), "+f"(d[35]), "+f"(d[36]), "+f"(d[37]), "+f"(d[38]), "+f"(d[39]),
        "+f"(d[40]), "+f"(d[41]), "+f"(d[42]), "+f"(d[43]), "+f"(d[44]), "+f"(d[45]), "+f"(d[46]), "+f"(d[47])
      : "l"(da), "l"(db), "r"(sc));
}

__device__ __forceinline__ void wgmma_ss_n128(float (&d)[64], uint64_t da, uint64_t db, int sc) {
  asm volatile("{\n.reg .pred p;\nsetp.ne.b32 p, %66, 0;\n"
      "wgmma.mma_async.sync.aligned.m64n128k16.f32.bf16.bf16 "
      "{%0,%1,%2,%3,%4,%5,%6,%7,%8,%9,%10,%11,%12,%13,%14,%15,%16,%17,%18,%19,%20,%21,%22,%23,%24,%25,%26,%27,%28,%29,%30,%31,%32,%33,%34,%35,%36,%37,%38,%39,%40,%41,%42,%43,%44,%45,%46,%47,%48,%49,%50,%51,%52,%53,%54,%55,%56,%57,%58,%59,%60,%61,%62,%63}, "
      "%64, %65, p, 1, 1, 0, 1;\n}\n"
      : "+f"(d[0]), "+f"(d[1]), "+f"(d[2]), "+f"(d[3]), "+f"(d[4]), "+f"(d[5]), "+f"(d[6]), "+f"(d[7]),
        "+f"(d[8]), "+f"(d[9]), "+f"(d[10]), "+f"(d[11]), "+f"(d[12]), "+f"(d[13]), "+f"(d[14]), "+f"(d[15]),
        "+f"(d[16]), "+f"(d[17]), "+f"(d[18]), "+f"(d[19]), "+f"(d[20]), "+f"(d[21]), "+f"(d[22]), "+f"(d[23]),
        "+f"(d[24]), "+f"(d[25]), "+f"(d[26]), "+f"(d[27]), "+f"(d[28]), "+f"(d[29]), "+f"(d[30]), "+f"(d[31]),
        "+f"(d[32]), "+f"(d[33]), "+f"(d[34]), "+f"(d[35]), "+f"(d[36]), "+f"(d[37]), "+f"(d[38]), "+f"(d[39]),
        "+f"(d[40]), "+f"(d[41]), "+f"(d[42]), "+f"(d[43]), "+f"(d[44]), "+f"(d[45]), "+f"(d[46]), "+f"(d[47]),
        "+f"(d[48]), "+f"(d[49]), "+f"(d[50]), "+f"(d[51]), "+f"(d[52]), "+f"(d[53]), "+f"(d[54]), "+f"(d[55]),
        "+f"(d[56]), "+f"(d[57]), "+f"(d[58]), "+f"(d[59]), "+f"(d[60]), "+f"(d[61]), "+f"(d[62]), "+f"(d[63])
      : "l"(da), "l"(db), "r"(sc));
}

__device__ __forceinline__ void wgmma_ss_n40(float (&d)[20], uint64_t da, uint64_t db, int sc) {
  asm volatile("{\n.reg .pred p;\nsetp.ne.b32 p, %22, 0;\n"
      "wgmma.mma_async.sync.aligned.m64n40k16.f32.bf16.bf16 "
      "{%0,%1,%2,%3,%4,%5,%6,%7,%8,%9,%10,%11,%12,%13,%14,%15,%16,%17,%18,%19}, "
      "%20, %21, p, 1, 1, 1, 1;\n}\n"
      : "+f"(d[0]), "+f"(d[1]), "+f"(d[2]), "+f"(d[3]), "+f"(d[4]), "+f"(d[5]), "+f"(d[6]), "+f"(d[7]),
        "+f"(d[8]), "+f"(d[9]), "+f"(d[10]), "+f"(d[11]), "+f"(d[12]), "+f"(d[13]), "+f"(d[14]), "+f"(d[15]),
        "+f"(d[16]), "+f"(d[17]), "+f"(d[18]), "+f"(d[19])
      : "l"(da), "l"(db), "r"(sc));
}

__device__ __forceinline__ void wgmma_rs_n8(float (&d)[4], const uint4& a, uint64_t db, int sc) {
  asm volatile("{\n.reg .pred p;\nsetp.ne.b32 p, %9, 0;\n"
      "wgmma.mma_async.sync.aligned.m64n8k16.f32.bf16.bf16 "
      "{%0,%1,%2,%3}, "
      "{%4,%5,%6,%7}, %8, p, 1, 1, 1;\n}\n"
      : "+f"(d[0]), "+f"(d[1]), "+f"(d[2]), "+f"(d[3])
      : "r"(a.x), "r"(a.y), "r"(a.z), "r"(a.w), "l"(db), "r"(sc));
}

__device__ __forceinline__ void wgmma_rs_n16(float (&d)[8], const uint4& a, uint64_t db, int sc) {
  asm volatile("{\n.reg .pred p;\nsetp.ne.b32 p, %13, 0;\n"
      "wgmma.mma_async.sync.aligned.m64n16k16.f32.bf16.bf16 "
      "{%0,%1,%2,%3,%4,%5,%6,%7}, "
      "{%8,%9,%10,%11}, %12, p, 1, 1, 1;\n}\n"
      : "+f"(d[0]), "+f"(d[1]), "+f"(d[2]), "+f"(d[3]), "+f"(d[4]), "+f"(d[5]), "+f"(d[6]), "+f"(d[7])
      : "r"(a.x), "r"(a.y), "r"(a.z), "r"(a.w), "l"(db), "r"(sc));
}

__device__ __forceinline__ void wgmma_rs_n24(float (&d)[12], const uint4& a, uint64_t db, int sc) {
  asm volatile("{\n.reg .pred p;\nsetp.ne.b32 p, %17, 0;\n"
      "wgmma.mma_async.sync.aligned.m64n24k16.f32.bf16.bf16 "
      "{%0,%1,%2,%3,%4,%5,%6,%7,%8,%9,%10,%11}, "
      "{%12,%13,%14,%15}, %16, p, 1, 1, 1;\n}\n"
      : "+f"(d[0]), "+f"(d[1]), "+f"(d[2]), "+f"(d[3]), "+f"(d[4]), "+f"(d[5]), "+f"(d[6]), "+f"(d[7]),
        "+f"(d[8]), "+f"(d[9]), "+f"(d[10]), "+f"(d[11])
      : "r"(a.x), "r"(a.y), "r"(a.z), "r"(a.w), "l"(db), "r"(sc));
}

struct Params {
  const __nv_bfloat16 *logA, *Aim, *Cre, *Cim, *logdt, *Dskip, *x, *wphi, *wo;
  __nv_bfloat16* out;
  uint4* xs;
  long long* ts;
};

__device__ __forceinline__ uint4 tr_row(const uint4 (&v)[8], int i) {
  uint32_t o[4];
#pragma unroll
  for (int m = 0; m < 4; m++) {
    const uint4 &ra = v[2 * m], &rb = v[2 * m + 1];
    const int k = i >> 1;
    const uint32_t xa = k == 0 ? ra.x : k == 1 ? ra.y : k == 2 ? ra.z : ra.w;
    const uint32_t xb = k == 0 ? rb.x : k == 1 ? rb.y : k == 2 ? rb.z : rb.w;
    o[m] = __byte_perm(xa, xb, (i & 1) ? 0x7632 : 0x5410);
  }
  return make_uint4(o[0], o[1], o[2], o[3]);
}

struct cpx { float r, i; };
__device__ __forceinline__ cpx csq(cpx a) { return {a.r * a.r - a.i * a.i, 2.f * (a.r * a.i)}; }
__device__ __forceinline__ cpx polar(float e, float t) {
  const float m = ex2(e);
  return {m * __cosf(t), m * __sinf(t)};
}

struct KgenRaw { unsigned short la, ai, cr, ci, ldt; };
__device__ __forceinline__ KgenRaw kgen_load(const Params& P, int d, int unit, int lane) {
  const int o = d * 128 + unit * 32 + lane;
  return {__ldg((const unsigned short*)P.logA + o), __ldg((const unsigned short*)P.Aim + o), __ldg((const unsigned short*)P.Cre + o),
          __ldg((const unsigned short*)P.Cim + o), __ldg((const unsigned short*)P.logdt + d)};
}
struct hmul { __half2 a, b; };
__device__ __forceinline__ hmul mk_mul(cpx w) {
  uint32_t b;
  asm("{\n.reg .f32 n;\nneg.ftz.f32 n, %1;\ncvt.rn.f16x2.f32 %0, %2, n;\n}\n" : "=r"(b) : "f"(w.i), "f"(w.r));
  return {__floats2half2_rn(w.r, w.i), *(const __half2*)&b};
}
__device__ __forceinline__ __half2 hcm(__half2 z, const hmul& w) { return __hfma2(__high2half2(z), w.b, __hmul2(__low2half2(z), w.a)); }
__device__ __forceinline__ uint32_t hu(__half2 v) { return *(const uint32_t*)&v; }

struct KgenAddr { uint32_t sa, sb, lb, lc, la; };
__device__ __forceinline__ KgenAddr kgen_addr(int lane, uint32_t buf) {
  KgenAddr a;
  a.sa = buf + (lane & 7) * 128 + ((((lane >> 3) ^ lane) & 7) << 4);
  a.lb = buf + (lane >> 3) * 128 + (((lane ^ (lane >> 3)) & 7) << 4);
  a.la = buf + ((lane >> 3) & 1) * 1024 + (lane >> 4) * 128 + (((lane ^ (lane >> 4)) & 7) << 4);
  a.sb = a.sa ^ 64; a.lc = a.lb ^ 64;
  asm volatile("" : "+r"(a.sa), "+r"(a.sb), "+r"(a.lb), "+r"(a.lc), "+r"(a.la));
  return a;
}
__device__ __forceinline__ void kgen_unit(const KgenRaw& r, const KgenAddr& ad, uint32_t zero, float (&k)[5][4], float& k2048, float& sc) {
  const float dt = bf_round(expf(bf_lo(r.ldt)));
  const float a2 = bf_round(ex2(bf_lo(r.la) * 1.4426950408889634f)) * (dt * -1.4426950408889634f);
  const float f = bf_lo(r.ai) * dt;
  const float r128 = f * 20.371832715762604f;
  const uint32_t ex = min(max(__reduce_max_sync(0xffffffffu, max(r.cr & 0x7fffu, r.ci & 0x7fffu)) >> 7, 1u), 253u);
  const float cs = uf((254u - ex) << 23);
  sc = 2.f * dt * uf(ex << 23);
  const cpx C = {bf_lo(r.cr) * cs, -bf_lo(r.ci) * cs};
  auto put = [&](const __half2 (&v)[8], uint32_t off) {
    stsm4(ad.sa + off, hu(v[0]), hu(v[1]), hu(v[2]), hu(v[3]));
    stsm4(ad.sb + off, hu(v[4]), hu(v[5]), hu(v[6]), hu(v[7]));
  };
  uint32_t A[4][4], B[5][2][4];
  auto get = [&](int j, uint32_t off) {
    __syncwarp();
    ldsm4(B[j][0], ad.lb + off);
    ldsm4(B[j][1], ad.lc + 512 + off);
  };
  auto tile = [&](int j) {
    k[j][0] = k[j][1] = k[j][2] = k[j][3] = 0.f;
#pragma unroll
    for (int s = 0; s < 4; s++) mma_h(k[j], A[s], B[j][s >> 1][2 * (s & 1)], B[j][s >> 1][2 * (s & 1) + 1]);
  };
  auto after = [&](cpx v, uint32_t dep) { return cpx{uf(fu(v.r) ^ (dep & zero)), v.i}; };
  const cpx w1 = polar(a2, f), w128 = polar(a2 * 128.f, (r128 - rintf(r128)) * 6.283185307179586f);
  const cpx w2 = csq(w1), w4 = csq(w2);
  __half2 t0[8], t1[8], t2[8], t3[8], t4[8];
  const hmul m2 = mk_mul(w2), m4 = mk_mul(w4), m128 = mk_mul(w128);
  t0[0] = __floats2half2_rn(1.f, 0.f); t0[1] = __floats2half2_rn(w1.r, w1.i); t0[2] = m2.a; t0[4] = m4.a;
  t0[3] = hcm(t0[1], m2); t0[5] = hcm(t0[1], m4); t0[6] = hcm(t0[2], m4); t0[7] = hcm(t0[3], m4);
  put(t0, 0); get(0, 0);
  t1[0] = m128.a;
#pragma unroll
  for (int i = 1; i < 8; i++) t1[i] = hcm(t0[i], m128);
  put(t1, 1024); get(1, 1024);
  {
    cpx w8 = csq(after(w4, B[0][0][0]));
    w8.i = -w8.i;
    const cpx w16 = csq(w8), w32 = csq(w16), w64 = csq(w32);
    const hmul m8 = mk_mul(w8), m16 = mk_mul(w16), m32 = mk_mul(w32), m64 = mk_mul(w64);
    __half2 a[8];
    a[0] = __floats2half2_rn(C.r, C.i); a[1] = hcm(a[0], m8);
    a[2] = hcm(a[0], m16); a[3] = hcm(a[1], m16);
#pragma unroll
    for (int i = 0; i < 4; i++) a[4 + i] = hcm(a[i], m32);
    put(a, 0);
#pragma unroll
    for (int i = 0; i < 8; i++) a[i] = hcm(a[i], m64);
    put(a, 1024);
    __syncwarp();
#pragma unroll
    for (int s = 0; s < 4; s++) ldsm4(A[s], (ad.la ^ (s << 5)) + s * 256);
  }
  const cpx w256 = csq(after(w128, B[1][0][0]));
  const hmul m256 = mk_mul(w256);
  t2[0] = m256.a;
#pragma unroll
  for (int i = 1; i < 8; i++) t2[i] = hcm((i & 1) ? t1[i & 6] : t0[i & 6], m256);
  put(t2, 0); get(2, 0);
  tile(0); tile(1);
  const cpx w512 = csq(after(w256, A[0][0]));
  const hmul m512 = mk_mul(w512);
  t3[0] = m512.a;
#pragma unroll
  for (int i = 1; i < 8; i++) t3[i] = hcm((i & 2) ? t2[i & 5] : ((i & 1) ? t1[i & 4] : t0[i & 4]), m512);
  put(t3, 1024); get(3, 1024);
  tile(2);
  const cpx w1024 = csq(after(w512, B[2][0][0])), we = csq(w1024);
  const hmul m1024 = mk_mul(w1024);
  t4[0] = m1024.a;
#pragma unroll
  for (int i = 1; i < 8; i++) t4[i] = hcm((i & 4) ? t3[i & 3] : ((i & 2) ? t2[i & 1] : t1[0]), m1024);
  put(t4, 0); get(4, 0);
  tile(3); tile(4);
  k2048 = (C.r * we.r + C.i * we.i) * sc;
}

__device__ __forceinline__ void build_tables(uint32_t tb, int lane, float (&k)[5][4], float k2048) {
  const int g = lane >> 2, c = lane & 3;
  const uint32_t kc = tb + T_KC + 16;
  {
    const uint32_t a0 = kc + 16 * g + 4 * c, a2 = kc + 2 * (256 + 4 * g + c);
    const uint32_t a3 = kc + 2 * (384 + 2 * g + 64 * (c & 1) + (c >> 1)), a4 = kc + 2 * (512 + g + 32 * c);
#pragma unroll
    for (int r = 0; r < 2; r++) {
      sts32(a0 + 128 * r, pack_bf(k[0][2 * r], k[0][2 * r + 1]));
      sts32(a0 + 128 * r + 256, pack_bf(k[1][2 * r], k[1][2 * r + 1]));
      const uint32_t w2 = pack_bf(k[2][2 * r], k[2][2 * r + 1]);
      const uint32_t w3 = pack_bf(k[3][2 * r], k[3][2 * r + 1]);
      const uint32_t w4 = pack_bf(k[4][2 * r], k[4][2 * r + 1]);
      sts16(a2 + 64 * r, w2); sts16(a2 + 64 * r + 128, w2 >> 16);
      sts16(a3 + 32 * r, w3); sts16(a3 + 32 * r + 64, w3 >> 16);
      sts16(a4 + 16 * r, w4); sts16(a4 + 16 * r + 32, w4 >> 16);
    }
  }
  if (lane == 0) { sts16(kc + 2 * 640, pack_bf(k2048, 0.f)); sts32(kc - 4, 0); }
  __syncwarp();
  const uint32_t td = tb + T_D + 32;
#pragma unroll
  for (int hf = 0; hf < 2; hf++) {
    const uint2 v = lds64(kc + 256 * hf + 8 * lane);
    const uint32_t pv = lds32(kc + 256 * hf + 8 * lane - 4);
    sts128(td + 512 * hf + 16 * lane, __byte_perm(v.x, pv, 0x7610), __byte_perm(v.x, v.x, 0x1032), __byte_perm(v.y, v.x, 0x7610),
           __byte_perm(v.y, v.y, 0x1032));
  }
#pragma unroll
  for (int hf = 0; hf < 2; hf++) {
    const uint32_t v = lds32(kc + 512 + 128 * hf + 4 * lane), nx = lds32(kc + 516 + 128 * hf + 4 * lane);
    uint32_t w0 = __byte_perm(v, v, 0x1010);
    const uint32_t w1 = w0;
    if (hf == 0) { const uint32_t pv = lds32(kc + 508); if (lane == 0) w0 = __byte_perm(v, pv, 0x7610); }
    sts128(td + 1024 + 512 * hf + 16 * lane, w0, w1, __byte_perm(v, v, 0x1032), __byte_perm(nx, v, 0x7610));
  }
  {
    const uint32_t kk = lds16(kc + 2 * 384);
    const uint32_t w = lane < 3 ? (kk | (kk << 16)) : (lane == 3 ? (kk << 16) : 0u);
    if (lane < 24) sts32(td + 4 * (lane < 16 ? 512 + lane : lane - 24), w);
    const uint32_t lo_ = lds16(kc + 2 * 511), le_ = lds16(kc + 2 * 512);
    const uint32_t ja = tb + T_5 + (lane < 16 ? 4 * lane : 256 + 4 * lane);
    sts32(ja, lane == 16 ? (le_ << 16) : 0u);
    sts32(ja + 384, lane == 16 ? (lo_ << 16) : 0u);
    sts32(tb + (lane < 16 ? T_7 : T_9 - 64) + 4 * lane, 0u);
  }
#pragma unroll
  for (int s = 0; s < 2; s++) {
    const uint32_t b = kc + 2 * (s ? 512 : 384) + 8 * lane;
    const uint2 v = lds64(b);
    uint32_t em = lds16(b - 2), e0 = v.x;
    const uint32_t e4 = lds16(b + 8);
    if (lane == 0) { em = 0; e0 = 0; }
    sts64(tb + (s ? T_7 : T_3) + 64 + 8 * lane, __byte_perm(v.x, em, 0x5432), __byte_perm(v.y, v.x, 0x7632));
    sts64(tb + (s ? T_9 : T_5) + 64 + 8 * lane, __byte_perm(v.y, e0, 0x5410), __byte_perm(e4, v.y, 0x5410));
  }
  __syncwarp();
}

__device__ __forceinline__ uint32_t box2w(int lo, int n, int o) {
  return ((unsigned)(o - lo) < (unsigned)n ? 0x3F80u : 0u) | ((unsigned)(o + 1 - lo) < (unsigned)n ? 0x3F800000u : 0u);
}

#define SPLIT() asm volatile("{\n.reg .pred p;\nsetp.ne.u32 p, %0, 0;\n@p exit;\n}\n" ::"r"(blockIdx.y) : "memory")

__device__ __forceinline__ void conv_channel(uint32_t ub, uint32_t tb, int lane, uint4* ydst) {
  const int g = lane >> 2, c = lane & 3, x = g - 2 * c;
  const int mi = lane >> 3;
  const uint32_t qa = ub + U_PAD + 16 * (lane & 7) + ((mi == 0 || mi == 3) ? U_ODD : 0) - (mi == 0 ? 16 : 0);
  const uint32_t hb = ub + U_PAD + (mi & 1) * U_ODD + 16 * ((lane >> 4) + (lane & 7)) - 16;
  const uint32_t kv = lds16(tb + T_KC + 16 + 2 * 512);
  const int oh = c < 2 ? 8 + 2 * c : 2 * c - 8, og = c < 3 ? 2 * c : -10;
  uint32_t bx[4] = {box2w(g - 4, 9, 2 * c), box2w(g - 3, 7, 2 * c), box2w(g - 4, 9, oh), box2w(g - 3, 7, oh)};
  uint32_t by[4] = {box2w(g - 10, 5, 2 * c - 8), box2w(g - 5, 3, 2 * c - 8), box2w(g - 10, 5, og), box2w(g - 5, 3, og)};
  uint32_t lb0 = ((unsigned)(x + 5) < 2u ? kv : 0u) | ((unsigned)(x + 4) < 2u ? kv << 16 : 0u);
  uint32_t lb1 = ((unsigned)(x - 3) < 2u ? kv : 0u) | ((unsigned)(x - 4) < 2u ? kv << 16 : 0u);
  const int q0 = g - 1, q1 = c < 3 ? g : g - 2;
  uint32_t y0a = ub + U_PAD + (q0 & 1) * U_ODD + 16 * (q0 >> 1) + 4 * c;
  uint32_t y1a = ub + U_PAD + (q1 & 1) * U_ODD + 16 * (q1 >> 1) + 4 * c;
#pragma unroll
  for (int i = 0; i < 4; i++) asm volatile("" : "+r"(bx[i]), "+r"(by[i]));
  asm volatile("" : "+r"(lb0), "+r"(lb1), "+r"(y0a), "+r"(y1a));
  mbar_wait(BAR(MB_UFULL));
  mbar_wait(BAR(MB_EMPTY + 15));
  TS(36);
  float acc[16][4];
  {
    uint32_t z09[8], z07[8], zm9[8], zm7[8];
#pragma unroll
    for (int i = 0; i < 8; i++) {
      uint32_t h[4];
      ldsm4(h, hb + 128 * i);
      float y0, y1, y2, y3, w0, w1, w2, w3;
      mma0(y0, y1, y2, y3, bx[0], bx[1], bx[2], bx[3], h[2], c < 2 ? h[3] : h[1]);
      mma0(w0, w1, w2, w3, bx[0], bx[1], bx[2], bx[3], h[1], c < 2 ? h[2] : h[0]);
      z09[i] = pack_bf(y0, y1); z07[i] = pack_bf(y2, y3);
      zm9[i] = pack_bf(w0, w1); zm7[i] = pack_bf(w2, w3);
    }
  uint32_t f3[3][4][4];
  {
    const uint32_t fa = tb + T_7 + 4 * (16 + x);
#pragma unroll
    for (int tt = 0; tt < 3; tt++)
#pragma unroll
      for (int D = 0; D < 4; D++) {
        const uint32_t a = fa + (tt == 0 ? 316 : (tt == 1 ? 320 : 0)) + 64 * D;
        f3[tt][D][0] = lds32(a); f3[tt][D][1] = lds32(a + 32); f3[tt][D][2] = lds32(a - 32); f3[tt][D][3] = lds32(a);
      }
  }
    float a[4][2][4];
#pragma unroll
    for (int kap = 0; kap < 4; kap++)
#pragma unroll
      for (int sg = 0; sg < 2; sg++)
#pragma unroll
        for (int bk = 3; bk >= kap; bk--) {
          const uint32_t(&q0_)[4] = f3[sg ? 2 : 0][bk - kap];
          const uint32_t(&q1_)[4] = f3[sg ? 2 : 1][bk - kap];
          float(&a0)[4] = a[bk][0];
          float(&a1)[4] = a[bk][1];
          if (sg == 0 && kap == 0) {
            mma0(a0[0], a0[1], a0[2], a0[3], q0_[0], q0_[1], q0_[2], q0_[3], z09[0], z09[1]);
            mma0(a1[0], a1[1], a1[2], a1[3], q1_[0], q1_[1], q1_[2], q1_[3], zm9[0], zm9[1]);
          } else {
            mma(a0[0], a0[1], a0[2], a0[3], q0_[0], q0_[1], q0_[2], q0_[3], sg ? zm7[2 * kap] : z09[2 * kap], sg ? zm7[2 * kap + 1] : z09[2 * kap + 1]);
            mma(a1[0], a1[1], a1[2], a1[3], q1_[0], q1_[1], q1_[2], q1_[3], sg ? z07[2 * kap] : zm9[2 * kap], sg ? z07[2 * kap + 1] : zm9[2 * kap + 1]);
          }
        }
    SPLIT();
#pragma unroll
    for (int i = 0; i < 8; i++) {
      uint32_t h[4];
      ldsm4(h, qa + 128 * i);
      const float ci[4] = {a[i >> 1][0][2 * (i & 1)], a[i >> 1][0][2 * (i & 1) + 1], a[i >> 1][1][2 * (i & 1)], a[i >> 1][1][2 * (i & 1) + 1]};
      mmac(acc[8 + i], h[0], h[1], h[2], h[3], lb0, lb1, ci);
    }
  }
  TS(44);
  {
    uint2 a5[10], a3[10];
    const uint32_t aa = tb + T_5 + 4 * (8 + 2 * g - 2 * c);
#pragma unroll
    for (int m = 0; m < 10; m++) { a5[m] = lds64(aa + 32 * m); a3[m] = lds64(aa + 384 + 32 * m); }
    uint32_t x5[12][2], x3[12][2];
    auto ygen = [&](int kap) {
#pragma unroll
      for (int hh = 0; hh < 2; hh++) {
        float y0, y1, y2, y3;
        mma0(y0, y1, y2, y3, by[0], by[1], by[2], by[3], lds32(y0a + 128 * kap + 64 * hh), lds32(y1a + 128 * kap + 64 * hh));
        x5[kap][hh] = pack_bf(y0, y1);
        x3[kap][hh] = pack_bf(y2, y3);
      }
    };
    ygen(11); ygen(10); ygen(9); ygen(8);
#pragma unroll
    for (int kap = 11; kap >= 0; kap--) {
      if (kap >= 4) ygen(kap - 4);
#pragma unroll
      for (int sg = 0; sg < 2; sg++)
#pragma unroll
        for (int i = 4; i >= 0; i--) {
          const int be = kap + 4 + i;
          if (be <= 15) {
            const uint2 &hi = sg ? a3[2 * i + 1] : a5[2 * i + 1], &lo = sg ? a3[2 * i] : a5[2 * i];
            const uint32_t b0 = sg ? x3[kap][0] : x5[kap][0], b1 = sg ? x3[kap][1] : x5[kap][1];
            if (be < 8 && i == 0 && sg == 0) mma0(acc[be][0], acc[be][1], acc[be][2], acc[be][3], hi.x, hi.y, lo.x, lo.y, b0, b1);
            else mma(acc[be][0], acc[be][1], acc[be][2], acc[be][3], hi.x, hi.y, lo.x, lo.y, b0, b1);
          }
        }
    }
  }
  TS(45);
  {
    const uint32_t st = tb + T_ST + lane * 8;
#pragma unroll
    for (int be = 4; be < 12; be++) sts64(st + 256 * be, pack_bf(acc[be][0], acc[be][1]), pack_bf(acc[be][2], acc[be][3]));
    SPLIT();
    uint32_t F[66], qd[8][4];
    const uint32_t fa = tb + T_D + 32 + 4 * x;
#pragma unroll
    for (int i = 0; i < 32; i++) {
      const int s = 120 - (i >> 2) - 8 * (i & 3);
      uint32_t(&q)[4] = qd[i & 7];
      ldsm4(q, qa + 16 * s);
      const int m = 16 * (i & 3) + 2 * (i >> 2);
      F[m] = lds32(fa + 32 * m); F[m + 1] = lds32(fa + 32 * m + 32);
#pragma unroll
      for (int be = 15; be >= 12; be--) {
        const int de = 8 * be - s;
        if (de >= 0) mma(acc[be][0], acc[be][1], acc[be][2], acc[be][3], q[0], q[1], q[2], q[3], F[2 * de + 1], F[2 * de]);
      }
    }
    F[64] = lds32(fa + 32 * 64); F[65] = lds32(fa + 32 * 65);
    uint32_t qp = qa + 128 * 11, sta = st + 256 * 10;
    uint4* yd = ydst + 7 * 32;
#pragma unroll
    for (int i = 0; i < 6; i++) ldsm4(qd[i], qp - 16 * i);
    uint2 sv = lds64(sta + 256);
    float ci[4] = {bf_lo(sv.x), bf_hi(sv.x), bf_lo(sv.y), bf_hi(sv.y)};
    float T[5][4];
#pragma unroll
    for (int i = 0; i < 16; i++) T[i >> 2][i & 3] = acc[12 + (i >> 2)][i & 3];
    nb_sync(NB_YZ, 160);
    TS(46);
#pragma unroll 1
    for (int bp = 5; bp >= 0; bp--) {
      uint32_t held[2];
#pragma unroll
      for (int o = 1; o >= 0; o--) {
#pragma unroll
        for (int k = 4; k >= 1; k--) mmac(T[k], qd[0][0], qd[0][1], qd[0][2], qd[0][3], F[16 * k + 1], F[16 * k], T[k - 1]);
        mmac(T[0], qd[0][0], qd[0][1], qd[0][2], qd[0][3], F[1], F[0], ci);
        ldsm4(qd[6], qp - 16 * 6);
        ldsm4(qd[7], qp - 16 * 7);
        sv = lds64(sta);
#pragma unroll
        for (int i = 1; i < 8; i++) {
#pragma unroll
          for (int k = 3; k >= 0; k--)
            mma(T[k][0], T[k][1], T[k][2], T[k][3], qd[i][0], qd[i][1], qd[i][2], qd[i][3], F[16 * k + 2 * i + 1], F[16 * k + 2 * i]);
          if (i < 7) ldsm4(qd[i - 1], qp - 128 - 16 * (i - 1));
          if (i == 2) {
            const uint32_t w0 = pack_bf(T[4][0], T[4][1]), w1 = pack_bf(T[4][2], T[4][3]);
            if (o) { held[0] = w0; held[1] = w1; }
            else st_x(yd, nz(w0), w1, held[0], held[1]);
          }
          if (i == 4) {
            if (2 * bp + o <= 4) sv = make_uint2(0, 0);
            ci[0] = bf_lo(sv.x); ci[1] = bf_hi(sv.x); ci[2] = bf_lo(sv.y); ci[3] = bf_hi(sv.y);
          }
        }
        qp -= 128; sta -= 256;
      }
      yd -= 32;
    }
#pragma unroll
    for (int B = 1; B >= 0; B--)
      st_x(ydst + B * 32, nz(pack_bf(T[2 * B][0], T[2 * B][1])), pack_bf(T[2 * B][2], T[2 * B][3]),
           pack_bf(T[2 * B + 1][0], T[2 * B + 1][1]), pack_bf(T[2 * B + 1][2], T[2 * B + 1][3]));
  }
}

__device__ __forceinline__ void dual_exp(const uint32_t* w, uint32_t* e) {
  const float L = 1.44268798828125f;
  uint32_t mx = bmax2(bmax2(w[0], w[1]), bmax2(w[2], w[3]));
  uint32_t mn = bmin2(bmin2(w[0], w[1]), bmin2(w[2], w[3]));
  mx = bmax2(mx, __shfl_xor_sync(0xffffffffu, mx, 1));
  mn = bmin2(mn, __shfl_xor_sync(0xffffffffu, mn, 1));
  mx = bmax2(mx, __shfl_xor_sync(0xffffffffu, mx, 2));
  mn = bmin2(mn, __shfl_xor_sync(0xffffffffu, mn, 2));
  const float mx0 = bf_lo(mx) * -L, mx1 = bf_hi(mx) * -L, mn0 = bf_lo(mn) * L, mn1 = bf_hi(mn) * L;
#pragma unroll
  for (int i = 0; i < 2; i++) {
    const float a0 = bf_lo(w[2 * i]), a1 = bf_hi(w[2 * i]), b0 = bf_lo(w[2 * i + 1]), b1 = bf_hi(w[2 * i + 1]);
    e[2 * i] = pack_bf(ex2(fmaf(a0, L, mx0)), ex2(fmaf(b0, L, mx0)));
    e[2 * i + 1] = pack_bf(ex2(fmaf(a1, L, mx1)), ex2(fmaf(b1, L, mx1)));
    e[4 + 2 * i] = pack_bf(ex2(fmaf(a0, -L, mn0)), ex2(fmaf(b0, -L, mn0)));
    e[5 + 2 * i] = pack_bf(ex2(fmaf(a1, -L, mn1)), ex2(fmaf(b1, -L, mn1)));
  }
}
__device__ __forceinline__ void normalise(uint32_t* e, const float (&s)[4]) {
  const uint32_t r = pack_bf(rcp(s[0]), rcp(s[2]));
  const __nv_bfloat162 rr = *(const __nv_bfloat162*)&r;
#pragma unroll
  for (int i = 0; i < 4; i++) {
    const __nv_bfloat162 v = __hmul2(*(const __nv_bfloat162*)&e[i], (i & 1) ? __high2bfloat162(rr) : __low2bfloat162(rr));
    e[i] = *(const uint32_t*)&v;
  }
}
__host__ __device__ constexpr uint64_t qdesc(uint32_t addr) { return mkdesc(addr, 128, 256, 0); }

__global__ void __launch_bounds__(NTHREADS, 1)
fused_kernel(const Params P, const __grid_constant__ CUtensorMap mx, const __grid_constant__ CUtensorMap mw,
             const __grid_constant__ CUtensorMap mo, const __grid_constant__ CUtensorMap mu,
             const __grid_constant__ CUtensorMap mout, const __grid_constant__ CUtensorMap mw4) {
  constexpr uint32_t sb = SB;
  const int tid = threadIdx.x, lane = tid & 31;
  const int warp = __shfl_sync(0xffffffffu, tid >> 5, 0);
  const int b = blockIdx.x, oct = b >> 3, i8 = b & 7;
  const int rt = oct < 8 ? oct : 15 - oct;
  const int hp = (oct >> 3) * 8 + i8;

  const int wg = warp >> 2, w = warp & 3;
  const int d = b * 4 + ((tid >> 5) & 3);
  if (tid < 384) {
    asm volatile("prefetch.tensormap [%0];" ::"l"(&mu) : "memory");
    asm volatile("prefetch.tensormap [%0];" ::"l"(&mw) : "memory");
    asm volatile("prefetch.tensormap [%0];" ::"l"(&mx) : "memory");
    asm volatile("prefetch.tensormap [%0];" ::"l"(&mw4) : "memory");
  }
  if (warp == 12) {
    if (lane == 0) {
#pragma unroll
      for (int i = 0; i < 9; i++) mbar_init(BAR(i), 1);
      asm volatile("fence.mbarrier_init.release.cluster;" ::: "memory");
    }
    __syncwarp();
    if (lane < 9) mbar_expect(BAR(0) + 8 * lane, lane == 5 ? 65536 : ((lane == 0 || lane > 5) ? 16384 : 28672));
    __syncwarp();
    e_tma3d(sb + OFF_W, &mw, BAR(MB_FULL), hp * 32, 0, 0);
    e_tma2d(sb + OFF_X + 3 * 16384, &mx, BAR(MB_FULL), 0, rt * 256);
    nb_arrive(NB_PROD, 192);
  } else if (warp == 13) {
    if (lane == 0) {
#pragma unroll
      for (int i = 9; i < 39; i++) mbar_init(BAR(i), i < MB_EMPTY ? 1 : (i < MB_AUX ? 4 : 8));
      asm volatile("fence.mbarrier_init.release.cluster;" ::: "memory");
    }
    __syncwarp();
    if (lane < 9) mbar_expect(BAR(MB_FULL + 8) + 8 * lane, lane < 8 ? 16384 : 131072);
    nb_arrive(NB_PROD, 192);
  }
  const KgenRaw raw = kgen_load(P, d, tid >> 7, lane);
  const unsigned short dsk = __ldg((const unsigned short*)P.Dskip + d);
  const uint32_t tb = sb + OFF_T + w * T_CH;
  const uint32_t kp = wg >= 2 ? sb + OFF_STG0 + 16384 + w * 2048 : ((tb + 127) & ~127u) + wg * 2048;
  const KgenAddr kad = kgen_addr(lane, wg == 3 ? sb + OFF_X + 32768 + w * 2048 : kp);
  if (wg == 1) nb_sync(NB_PROD, 192);
  if (warp == 12) {
#pragma unroll 1
    for (int kb = 1; kb < 4; kb++) {
      if (kb == U_AT) e_tma4d(sb + OFF_STG0, &mu, BAR(MB_URAW), i8 * 64, oct * 2);
      e_tma3d(sb + OFF_W + kb * 12288, &mw, BAR(MB_FULL) + 8 * kb, hp * 32, kb * 64, 0);
      e_tma2d(sb + OFF_X + (kb < 2 ? kb + 3 : kb - 2) * 16384, &mx, BAR(MB_FULL) + 8 * kb, kb * 64, rt * 256);
    }
    e_prefetch(P.x + (size_t)(rt * 256 + hp * 16) * 512, 16384);
    e_tma4d(sb + OFF_W + 4 * 12288, &mw4, BAR(MB_FULL + 4), hp * 32, 4);
    if (smem_u32(smem_raw) != SB) __trap();
    if (lane == 0) TS1(54);
  }
  float k[5][4], k2048, ksc;
  kgen_unit(raw, kad, blockIdx.y, k, k2048, ksc);
  TS(40 + wg);
  if ((fu(k[0][0]) & fu(k[1][0]) & fu(k[2][0]) & fu(k[3][0]) & fu(k[4][0])) == 0xffffffffu) sts32(kp, 0);
  if (wg == 3) {
    nb_sync(0, 512);
    if (warp == 12) {
      asm volatile("fence.proxy.async.shared::cta;" ::: "memory");
      e_tma2d(sb + OFF_X + 2 * 16384, &mx, BAR(MB_FULL + 4), 256, rt * 256);
    }
  } else if (wg) {
    nb_arrive(0, 512);
  }
  k2048 += __shfl_xor_sync(0xffffffffu, k2048, 16);
  k2048 += __shfl_xor_sync(0xffffffffu, k2048, 8);
  if (wg != 2) {
    uint32_t h[10];
#pragma unroll
    for (int j = 0; j < 10; j++) h[j] = hu(__floats2half2_rn(k[j >> 1][2 * (j & 1)], k[j >> 1][2 * (j & 1) + 1]));
    sts128(kp + lane * 16, h[0], h[1], h[2], h[3]);
    sts128(kp + 512 + lane * 16, h[4], h[5], h[6], h[7]);
    sts128(kp + 1024 + lane * 16, h[8], h[9], fu(k2048), fu(ksc));
  }
  if (wg == 0) { nb_arrive(NB_PREP, 512); nb_sync(0, 512); }
  else if (wg != 2) nb_arrive(NB_PREP, 512);
  else nb_sync(NB_PREP, 512);
  if (warp >= 12) {
    asm volatile("setmaxnreg.dec.sync.aligned.u32 32;");
    if (warp == 12) {
      uint32_t slot = sb + OFF_X + 3 * 16384;
#pragma unroll 1
      for (int n = 0; n < 11; n++) {
        mbar_spin(BAR(MB_EMPTY) + 8 * n);
        const int m = n + 5;
        e_tma2d(slot, &mx, BAR(MB_FULL) + 8 * m, (m & 7) * 64, rt * 256 + (m >> 3) * 128);
        slot = slot == sb + OFF_X + 4 * 16384 ? sb + OFF_X : slot + 16384;
        if (n == 7) e_prefetch(P.wo + (size_t)b * 2048, 4096);
      }
#pragma unroll 1
      for (int i = 0; i < 8; i++) {
        mbar_wait(BAR(MB_EMPTY + 10) + 8 * ((0x54332100u >> (4 * i)) & 7));
        const int w0 = (0x54736210u >> (4 * i)) & 7;
        e_tma3d(sb + OFF_W + w0 * 16384, &mo, BAR(MB_WO), 0, w0 * 64, (hp & 3) * 2);
      }
    } else {
      if (warp == 15) {
        const uint4 v0 = __ldg((const uint4*)P.wphi + hp * 64 + lane), v1 = __ldg((const uint4*)P.wphi + hp * 64 + 32 + lane);
        sts128(sb + OFF_PHI + (lane & 1) * 256 + (lane >> 1) * 16, v0.x, v0.y, v0.z, v0.w);
        sts128(sb + OFF_PHI + 512 + (lane & 1) * 256 + (lane >> 1) * 16, v1.x, v1.y, v1.z, v1.w);
        const uint32_t one = (((lane >> 3) ^ (lane >> 4)) & 1) ? 0u : ((lane & 1) ? 0x3F800000u : 0x3F80u);
        const int q = (lane >> 1) & 3;
        sts128(sb + OFF_EYE + lane * 16, q == 0 ? one : 0u, q == 1 ? one : 0u, q == 2 ? one : 0u, q == 3 ? one : 0u);
        sts64(sb + OFF_ONE + lane * 8, 0x3F803F80u, 0x3F803F80u);
        asm volatile("fence.proxy.async.shared::cta;" ::: "memory");
        nb_arrive(NB_KREAD, 160);
        mbar_wait(BAR(MB_EMPTY + ZERO_STEP));
        uint4* py = P.xs + X_Y + b * 1024 + lane;
#pragma unroll 1
        for (int i = 0; i < 1024; i += 32) st_x(py + i, 0, 0, 0, 0);
        nb_arrive(NB_YZ, 160);
        nb_arrive(NB_ODONE, 320);
        if (lane == 0) TS1(55);
        return;
      }
      uint32_t* const cnt = (uint32_t*)(P.xs + X_CNT) + (warp == 13 ? i8 : 8 + rt) * 32;
      const unsigned target = (ld_x32(cnt) & ~15u) + 16;
      if (warp == 13) {
        uint4* pp = P.xs + X_PART + (hp * 8 + rt) * 144 + lane;
#pragma unroll 1
        for (int i = 0; i < 144; i += 32) if (i + lane < 144) st_x(pp + i, 0, 0, 0, 0);
      }
      nb_sync(warp == 13 ? NB_INIT : NB_ODONE, warp == 13 ? 160 : 320);
      if (lane == 0) TS1(warp == 13 ? 49 : 56);
      asm volatile("fence.proxy.async.shared::cta;" ::: "memory");
      if (lane == 0) asm volatile("red.release.gpu.global.add.u32 [%0], 1;" ::"l"(cnt) : "memory");
      if (lane == 0) TS1(warp == 13 ? 50 : 57);
      const uint32_t* pc = (warp == 13 && (lane & 1)) ? (uint32_t*)(P.xs + X_CNT) + (b >> 4) * 32 : cnt;
#pragma unroll 1
      for (int i = 0; i < SPIN_MAX; i++) {
        unsigned v;
        asm volatile("ld.acquire.gpu.global.u32 %0, [%1];" : "=r"(v) : "l"(pc) : "memory");
        if (__all_sync(0xffffffffu, (int)(v - target) >= 0)) break;
      }
      if (lane == 0) TS1(warp == 13 ? 51 : 58);
      asm volatile("fence.proxy.async.global;" ::: "memory");
      if (warp == 13) {
        mbar_wait(BAR(MB_EMPTY + 11));
        e_expect(BAR(MB_UFULL), 4 * U_CH);
        e_bulk(sb + OFF_U, P.xs + X_UT + b * (U_CH / 4), 4 * U_CH, BAR(MB_UFULL));
      } else {
        const uint4* src = P.xs + X_O + (rt * 4 + (hp >> 2)) * 4096;
        e_expect(BAR(MB_OA), 14336);
        e_bulk(sb + OFF_STG0, src + 3200, 14336, BAR(MB_OA));
        e_expect(BAR(MB_OC), 32768);
        e_bulk(sb + OFF_X + 32768, src, 32768, BAR(MB_OC));
        nb_sync(NB_BDONE, 288);
        asm volatile("fence.proxy.async.shared::cta;" ::: "memory");
        e_expect(BAR(MB_OB), 18432);
        e_bulk(sb + OFF_U, src + 2048, 18432, BAR(MB_OB));
      }
    }
    return;
  }

  const int t = tid & 127;
  const int g = lane >> 2, c = lane & 3;
  {
    if (wg == 2) {
      asm volatile("setmaxnreg.inc.sync.aligned.u32 160;");
#pragma unroll
      for (int j = 0; j < 5; j++) { k[j][0] *= ksc; k[j][1] *= ksc; k[j][2] *= ksc; k[j][3] *= ksc; }
#pragma unroll 1
      for (int q = 0; q < 3; q++) {
        const uint32_t src = (q == 2 ? kp : ((tb + 127) & ~127u) + q * 2048) + lane * 16;
        const uint4 v0 = lds128(src), v1 = lds128(src + 512), v2 = lds128(src + 1024);
        const uint32_t h[10] = {v0.x, v0.y, v0.z, v0.w, v1.x, v1.y, v1.z, v1.w, v2.x, v2.y};
#pragma unroll
        for (int j = 0; j < 10; j++) {
          const float2 f = __half22float2(*(const __half2*)&h[j]);
          k[j >> 1][2 * (j & 1)] = fmaf(f.x, uf(v2.w), k[j >> 1][2 * (j & 1)]);
          k[j >> 1][2 * (j & 1) + 1] = fmaf(f.y, uf(v2.w), k[j >> 1][2 * (j & 1) + 1]);
        }
        k2048 += uf(v2.z);
      }
#pragma unroll
      for (int o2 = 4; o2; o2 >>= 1) k2048 += __shfl_xor_sync(0xffffffffu, k2048, o2);
      if (lane == 0) k[0][0] += bf_lo(dsk);
      __syncwarp();
      if (lane == 0) mbar_arrive(BAR(MB_AUX));
      TS(34);
      build_tables(tb, lane, k, k2048);
      TS(35);
      uint4* const g_y = P.xs + X_Y;
      conv_channel(sb + OFF_U + w * U_CH, tb, lane, g_y + (size_t)d * 256 + lane);
      nb_arrive(NB_BDONE, 288);
      TS(37);
      mbar_wait(BAR(MB_OA));
      const int lam = w * 8 + g;
      const uint4* src = g_y + (size_t)(oct * 32 + c * 8) * 256 + i8 * 32 + lam;
      uint4 v[8];
#pragma unroll 1
      for (int it = 0; it < SPIN_MAX; it++) {
        uint32_t m = 0xffffffffu;
#pragma unroll
        for (int i = 0; i < 8; i++) v[i] = ld_x(src + i * 256);
#pragma unroll
        for (int i = 0; i < 8; i++) m = min(m, v[i].x);
        if (__all_sync(0xffffffffu, m != 0)) break;
      }
      __nv_bfloat16* dst = P.out + (size_t)(i8 * 256 + (lam >> 2) * 16 + (lam & 3) * 2) * 1024 + 512 + oct * 32 + c * 8;
#pragma unroll
      for (int i = 0; i < 8; i++) *(uint4*)(dst + (size_t)((i >> 2) * 128 + ((i >> 1) & 1) * 8 + (i & 1)) * 1024) = tr_row(v, i);
      TS(38);
      GT(63);
      if (w == 0) TSDUMP(32);
      return;
    }
    if (wg == 1) {
      mbar_wait(BAR(MB_URAW));
      TS(48);
      uint4* dst = P.xs + X_UT + (i8 * 64 + g) * (U_CH / 16) + (w & 1) * (U_ODD / 16) + U_PAD / 16 + oct * 8 + (w >> 1) * 4 + c;
      const int ln = ((lane >> 1) & 3) + 4 * (lane & 1);
      uint32_t r[8][4];
#pragma unroll
      for (int i = 0; i < 8; i++) ldsm4t(r[i], sb + OFF_STG0 + w * 4096 + ((lane >> 3) * 8 + ln) * 128 + ((i ^ ln) << 4));
#pragma unroll
      for (int i = 0; i < 8; i++) dst[i * (U_CH / 2)] = make_uint4(r[i][0], r[i][1], r[i][2], r[i][3]);
      nb_arrive(NB_INIT, 160);
      if (lane == 0) mbar_arrive(BAR(MB_AUX));
      mbar_wait(BAR(MB_EMPTY + 4));
      mbar_spin(BAR(MB_EMPTY + 6));
    }
    TS(wg * 16 + 1);
  }

  float acc[2][48];
  {
    uint32_t fb = BAR(MB_FULL) + 64 * wg;
    uint32_t da = (uint32_t)mkdesc(sb + OFF_X, 16, 0, 0) + (wg ? 1024 : 3072), db = (uint32_t)mkdesc(sb + OFF_W, 4096, 0, 0);
    constexpr uint64_t ha = mkdesc(0, 0, 1024, 1), hb = mkdesc(0, 0, 512, 2);
    mbar_spin(fb);
    TS(wg * 16 + 2);
#pragma unroll 1
    for (int kb = 0; kb < 8; kb++) {
      WG_FENCE();
#pragma unroll
      for (int k = 0; k < 4; k++) {
        wgmma_ss_n96(acc[0], ha | (da + 2 * k), hb | (db + 64 * k), k ? 1 : kb);
        wgmma_ss_n96(acc[1], ha | (da + 2 * k + 512), hb | (db + 64 * k), k ? 1 : kb);
      }
      WG_COMMIT();
      if (kb < 7) mbar_spin(fb + 8);
      WG_WAIT(1);
      if (kb > 0) e_arrive(fb + 8 * (MB_EMPTY - MB_FULL - 1));
      fb += 8; db += 768;
      da = da == (uint32_t)mkdesc(sb + OFF_X + 65536, 16, 0, 0) ? da - 4096 : da + 1024;
    }
    if (wg == 0) nb_sync(NB_KREAD, 160);
    WG_WAIT(0);
    e_arrive(fb + 8 * (MB_EMPTY - MB_FULL - 1));
    mbar_spin(fb + 8 * (MB_EMPTY - MB_FULL - 1));
  }
  TS(wg * 16 + 3);
  asm volatile("setmaxnreg.inc.sync.aligned.u32 160;");

  constexpr uint32_t stg0 = sb + OFF_STG0, stg1 = sb + OFF_X + 32768;
  uint4* const g_part = P.xs + X_PART;
  uint4* const g_o = P.xs + X_O;
  constexpr uint32_t kvs = stg0;
  auto pack8 = [](const float* a) { return make_uint4(pack_bf(a[0], a[1]), pack_bf(a[2], a[3]), pack_bf(a[4], a[5]), pack_bf(a[6], a[7])); };
  auto feat = [&](const uint4 (&af)[4], float (&p)[4][8]) {
    WG_FENCE();
#pragma unroll
    for (int u = 0; u < 4; u++) wgmma_rs_n16(p[u], af[u], qdesc(sb + OFF_PHI + (u & 1) * 512), 0);
    WG_COMMIT();
  };
  auto packp = [](const float (&p)[4][8], uint32_t (&pw)[16]) {
#pragma unroll
    for (int i = 0; i < 16; i++) pw[i] = pack_bf(p[i >> 2][(i & 1) + 2 * (i & 2)], p[i >> 2][(i & 1) + 2 * (i & 2) + 2]);
  };
  auto contract = [&](float (&kc)[20], uint32_t stg, int acc_in) {
    WG_FENCE();
#pragma unroll
    for (int s = 0; s < 8; s++) wgmma_ss_n40(kc, qdesc(stg + s * SLAB), qdesc(stg + s * SLAB + 2048), s ? 1 : acc_in);
    WG_COMMIT();
    WG_WAIT(0);
  };
  uint32_t eq[32];
  {
    uint4 af[4], aq[4], vp[4];
    float p[4][8];
#pragma unroll
    for (int u = 0; u < 4; u++) af[u] = pack8(acc[u >> 1] + 16 + 8 * (u & 1));
    feat(af, p);
#pragma unroll
    for (int u = 0; u < 4; u++) { aq[u] = pack8(acc[u >> 1] + 8 * (u & 1)); vp[u] = pack8(acc[u >> 1] + 32 + 8 * (u & 1)); }
    WG_WAIT(0);
    uint32_t pw[16], ek[32];
    packp(p, pw);
#pragma unroll
    for (int u = 0; u < 4; u++) dual_exp(pw + 4 * u, ek + 8 * u);
    TS(wg * 16 + 12);
    float rs[8][4];
    WG_FENCE();
#pragma unroll
    for (int i = 0; i < 8; i++) wgmma_rs_n8(rs[i], make_uint4(ek[4 * i], ek[4 * i + 1], ek[4 * i + 2], ek[4 * i + 3]), qdesc(sb + OFF_ONE), 0);
    WG_COMMIT();
    feat(aq, p);
    WG_WAIT(0);
#pragma unroll
    for (int i = 0; i < 8; i++) normalise(ek + 4 * i, rs[i]);
    packp(p, pw);
    mbar_wait(BAR(MB_AUX));
    const uint32_t sl = (wg ? stg1 : stg0) + w * SLAB + lane * 16;
#pragma unroll
    for (int i = 0; i < 8; i++) stsm4(sl + (i >> 2) * 4 * SLAB + (i & 3) * 512, ek[4 * i], ek[4 * i + 1], ek[4 * i + 2], ek[4 * i + 3]);
#pragma unroll
    for (int i = 0; i < 4; i++) stsm4(sl + (i >> 1) * 4 * SLAB + 2048 + (i & 1) * 512, vp[i].x, vp[i].y, vp[i].z, vp[i].w);
    sts128(sl + (lane >> 4) * (4 * SLAB - 256) + 3072, 0x3F803F80u, 0x3F803F80u, 0x3F803F80u, 0x3F803F80u);
    asm volatile("fence.proxy.async.shared::cta;" ::: "memory");
    TS(wg * 16 + 13);
    if (wg) {
      nb_arrive(NB_ST0, 256);
    } else {
      float kc[20];
      uint4* pp = g_part + (size_t)(hp * 8 + rt) * 144 + t;
      uint32_t* pz = (uint32_t*)(pp - t + 128) + w * 16 + c * 8 + g;
      asm volatile("" : "+l"(pp), "+l"(pz));
      nb_sync(NB_WG0, 128);
      contract(kc, stg0, 0);
      mbar_wait(BAR(MB_UFULL));
      TS(15);
      nb_sync(NB_ST0, 256);
      contract(kc, stg1, 1);
      TS(6);
      float kv[8];
#pragma unroll
      for (int i = 0; i < 8; i++) kv[i] = w & 2 ? kc[8 + i] : kc[i];
      st_x(pp, nz(pack_bf(kv[0], kv[1])), pack_bf(kv[2], kv[3]), pack_bf(kv[4], kv[5]), pack_bf(kv[6], kv[7]));
      if (c < 2) st_x32(pz, nz(fu(c ? kc[18] : kc[16])));
      TS(5);
    }
#pragma unroll
    for (int u = 0; u < 4; u++) dual_exp(pw + 4 * u, eq + 8 * u);
  }
  TS(wg * 16 + 4);
  if (wg == 1) {
    mbar_wait(BAR(MB_UFULL));
    const uint4* ps = g_part + (size_t)hp * 8 * 144 + t;
    const uint32_t* zs = (const uint32_t*)(g_part + (size_t)(hp * 8 + (lane >> 4) * 4) * 144 + 128) + w * 16 + (lane & 15);
    uint4 v[8];
    uint32_t zv[4];
#pragma unroll 1
    for (int it = 0; it < SPIN_MAX; it++) {
#pragma unroll
      for (int i = 0; i < 8; i++) v[i] = ld_x(ps + i * 144);
#pragma unroll
      for (int i = 0; i < 4; i++) zv[i] = ld_x32(zs + i * 576);
      uint32_t m = min(min(zv[0], zv[1]), min(zv[2], zv[3]));
#pragma unroll
      for (int i = 0; i < 8; i++) m = min(m, v[i].x);
      if (__all_sync(0xffffffffu, m != 0)) break;
    }
    float s[8];
    WG_FENCE();
#pragma unroll
    for (int r = 0; r < 8; r++) wgmma_rs_n16(s, v[r], qdesc(sb + OFF_EYE), r);
    WG_COMMIT();
    float zsum = (uf(zv[0]) + uf(zv[1])) + (uf(zv[2]) + uf(zv[3]));
    zsum += __shfl_xor_sync(0xffffffffu, zsum, 16);
    const uint32_t z1 = pack_bf(zsum, 1.f);
    if (lane < 16) sts128(kvs + w * 768 + 512 + lane * 16, z1, z1, z1, z1);
    WG_WAIT(0);
    stsm4(kvs + w * 768 + lane * 16, pack_bf(s[0], s[1]), pack_bf(s[2], s[3]), pack_bf(s[4], s[5]), pack_bf(s[6], s[7]));
    asm volatile("fence.proxy.async.shared::cta;" ::: "memory");
    TS(22);
  }
  nb_sync(NB_KV, 256);
  {
    float n[8][12];
    WG_FENCE();
#pragma unroll
    for (int i = 0; i < 8; i++) wgmma_rs_n24(n[i], make_uint4(eq[4 * i], eq[4 * i + 1], eq[4 * i + 2], eq[4 * i + 3]), qdesc(kvs + (i & 3) * 768), 0);
    WG_COMMIT();
    uint32_t* od = (uint32_t*)(g_o + (size_t)((rt * 4 + wg * 2) * 32 + hp * 2) * 128) + w * 64 + lane;
    WG_WAIT(0);
#pragma unroll
    for (int u = 0; u < 4; u++) {
      float(&np)[12] = n[2 * u];
      const float(&nm)[12] = n[2 * u + 1];
      const float q0 = np[9] * rcp(nm[9]), q1 = np[11] * rcp(nm[11]);
      const float r0 = rcp(fmaf(nm[8], q0, fmaf(np[9], 1e-6f, np[8]))), r1 = rcp(fmaf(nm[10], q1, fmaf(np[11], 1e-6f, np[10])));
#pragma unroll
      for (int i = 0; i < 8; i++) np[i] = fmaf(nm[i], (i & 2) ? q1 : q0, np[i]);
      uint32_t* o = od + (u >> 1) * 16384 + (u & 1) * 512;
      o[0] = pack_bf(np[0] * r0, np[1] * r0);
      o[32] = pack_bf(np[2] * r1, np[3] * r1);
      o[256] = pack_bf(np[4] * r0, np[5] * r0);
      o[288] = pack_bf(np[6] * r1, np[7] * r1);
    }
  }
  TS(wg * 16 + 7);
  nb_arrive(NB_ODONE, 320);
  if (wg) { if (w == 0) TSDUMP(16); return; }
  mbar_wait(BAR(MB_WO));
  mbar_wait(BAR(MB_OA));
  TS(8);
  nb_sync(NB_BDONE, 288);
  TS(9);
  float oc[64];
  {
    constexpr uint64_t ha = mkdesc(0, 0, 128, 0), hb = mkdesc(0, 0, 1024, 1);
    constexpr uint32_t da0 = (uint32_t)mkdesc(stg1, 1024, 0, 0), db0 = (uint32_t)mkdesc(sb + OFF_W, 8192, 0, 0);
#pragma unroll 1
    for (int j = 0; j < 8; j++) {
      const int kb = (j + 7) & 7;
      if ((j & 3) == 1) mbar_spin(j == 1 ? BAR(MB_OC) : BAR(MB_OB));
      WG_FENCE();
#pragma unroll
      for (int k = 0; k < 4; k++) wgmma_ss_n128(oc, ha | (da0 + 512 * kb + 128 * k), hb | (db0 + 1024 * kb + 128 * k), k ? 1 : j);
      WG_COMMIT();
    }
    WG_WAIT(0);
  }
  TS(10);
  nb_sync(NB_WG0, 128);
  const uint32_t ot = sb + OFF_W + w * 4096;
#pragma unroll
  for (int i = 0; i < 16; i += 2)
    stsm4(ot + (i >> 3) * 2048 + (lane & 15) * 128 + (((i + (lane >> 4)) ^ lane) & 7) * 16, pack_bf(oc[4 * i], oc[4 * i + 1]),
          pack_bf(oc[4 * i + 2], oc[4 * i + 3]), pack_bf(oc[4 * i + 4], oc[4 * i + 5]), pack_bf(oc[4 * i + 6], oc[4 * i + 7]));
  asm volatile("fence.proxy.async.shared::cta;" ::: "memory");
  __syncwarp();
  e_store3d(&mout, ot, (rt * 4 + (hp >> 2)) * 64 + w * 16, (hp & 3) * 2);
  TS(wg * 16 + 11);
  GT(61 + wg);
  if (w == 0) TSDUMP(0);
  if (w == 1) TSDUMP(48);
}

typedef CUresult (*EncodeFn)(CUtensorMap*, CUtensorMapDataType, cuuint32_t, void*, const cuuint64_t*, const cuuint64_t*,
                             const cuuint32_t*, const cuuint32_t*, CUtensorMapInterleave, CUtensorMapSwizzle,
                             CUtensorMapL2promotion, CUtensorMapFloatOOBfill);

}

extern "C" void kernel_launch(void* const* d_in, const int* in_sizes, int n_in, void* d_out, int out_size) {
  (void)in_sizes; (void)n_in; (void)out_size;
  void* fn = nullptr;
  cudaDriverEntryPointQueryResult qr;
  cudaGetDriverEntryPoint("cuTensorMapEncodeTiled", &fn, cudaEnableDefault, &qr);
  EncodeFn enc = (EncodeFn)fn;
  CUtensorMap mx, mw, mo, mu, mout, mw4;
  const cuuint32_t es[5] = {1, 1, 1, 1, 1};
  {
    cuuint64_t dims[2] = {512, 2048}, st[1] = {1024};
    cuuint32_t box[2] = {64, 128};
    enc(&mx, CU_TENSOR_MAP_DATA_TYPE_BFLOAT16, 2, d_in[0], dims, st, box, es, CU_TENSOR_MAP_INTERLEAVE_NONE,
        CU_TENSOR_MAP_SWIZZLE_128B, CU_TENSOR_MAP_L2_PROMOTION_L2_128B, CU_TENSOR_MAP_FLOAT_OOB_FILL_NONE);
  }
  {
    cuuint64_t dims[3] = {512, 512, 3}, st[2] = {3072, 1024};
    cuuint32_t box[3] = {32, 64, 3};
    enc(&mw, CU_TENSOR_MAP_DATA_TYPE_BFLOAT16, 3, d_in[1], dims, st, box, es, CU_TENSOR_MAP_INTERLEAVE_NONE,
        CU_TENSOR_MAP_SWIZZLE_64B, CU_TENSOR_MAP_L2_PROMOTION_L2_128B, CU_TENSOR_MAP_FLOAT_OOB_FILL_NONE);
  }
  {
    cuuint64_t dims[3] = {64, 512, 8}, st[2] = {1024, 128};
    cuuint32_t box[3] = {64, 64, 2};
    enc(&mo, CU_TENSOR_MAP_DATA_TYPE_BFLOAT16, 3, d_in[3], dims, st, box, es, CU_TENSOR_MAP_INTERLEAVE_NONE,
        CU_TENSOR_MAP_SWIZZLE_128B, CU_TENSOR_MAP_L2_PROMOTION_L2_128B, CU_TENSOR_MAP_FLOAT_OOB_FILL_NONE);
  }
  {
    cuuint64_t dims[4] = {512, 4, 16, 32}, st[3] = {16384, 1024, 65536};
    cuuint32_t box[4] = {64, 4, 16, 2};
    enc(&mu, CU_TENSOR_MAP_DATA_TYPE_BFLOAT16, 4, d_in[4], dims, st, box, es, CU_TENSOR_MAP_INTERLEAVE_NONE,
        CU_TENSOR_MAP_SWIZZLE_128B, CU_TENSOR_MAP_L2_PROMOTION_L2_128B, CU_TENSOR_MAP_FLOAT_OOB_FILL_NONE);
  }
  {
    cuuint64_t dims[3] = {64, 2048, 16}, st[2] = {2048, 128};
    cuuint32_t box[3] = {64, 16, 2};
    enc(&mout, CU_TENSOR_MAP_DATA_TYPE_BFLOAT16, 3, d_out, dims, st, box, es, CU_TENSOR_MAP_INTERLEAVE_NONE,
        CU_TENSOR_MAP_SWIZZLE_128B, CU_TENSOR_MAP_L2_PROMOTION_NONE, CU_TENSOR_MAP_FLOAT_OOB_FILL_NONE);
  }
  {
    cuuint64_t dims[4] = {512, 64, 3, 8}, st[3] = {3072, 1024, 64 * 3072};
    cuuint32_t box[4] = {32, 64, 3, 4};
    enc(&mw4, CU_TENSOR_MAP_DATA_TYPE_BFLOAT16, 4, d_in[1], dims, st, box, es, CU_TENSOR_MAP_INTERLEAVE_NONE,
        CU_TENSOR_MAP_SWIZZLE_64B, CU_TENSOR_MAP_L2_PROMOTION_L2_128B, CU_TENSOR_MAP_FLOAT_OOB_FILL_NONE);
  }
  Params P;
  P.x = (const __nv_bfloat16*)d_in[0];
  P.wphi = (const __nv_bfloat16*)d_in[2];
  P.wo = (const __nv_bfloat16*)d_in[3];
  P.logA = (const __nv_bfloat16*)d_in[5];
  P.Aim = (const __nv_bfloat16*)d_in[6];
  P.Cre = (const __nv_bfloat16*)d_in[7];
  P.Cim = (const __nv_bfloat16*)d_in[8];
  P.logdt = (const __nv_bfloat16*)d_in[9];
  P.Dskip = (const __nv_bfloat16*)d_in[10];
  P.out = (__nv_bfloat16*)d_out;
  cudaGetSymbolAddress((void**)&P.xs, g_x);
  P.ts = nullptr;
  cudaFuncSetAttribute(fused_kernel, cudaFuncAttributeMaxDynamicSharedMemorySize, SMEM_BYTES);
  fused_kernel<<<NCTA, NTHREADS, SMEM_BYTES>>>(P, mx, mw, mo, mu, mout, mw4);
}
```

```cpp
#include <cuda_runtime.h>
#include <cuda_bf16.h>
#include <cuda_fp16.h>
#include <cuda.h>
#include <stdint.h>

#define DBG_TS 0

namespace {

constexpr int NTHREADS = 512;
constexpr int NCTA = 128;
constexpr int OFF_W = 0;
constexpr int OFF_X = 98304;
constexpr int OFF_U = OFF_X + 65536;
constexpr int U_CH = 4416, U_ODD = 2240, U_PAD = 128;
constexpr int OFF_STG0 = OFF_U + 18432;
constexpr int SLAB = 3328;
constexpr int OFF_T = OFF_STG0 + 8 * SLAB;
constexpr int T_CH = 5216;
constexpr int T_D = 0;
constexpr int T_5 = 2144;
constexpr int T_3 = T_5 + 384;
constexpr int T_7 = T_5 + 1024;
constexpr int T_9 = T_7 + 320;
constexpr int T_KC = T_9 + 320;
constexpr int T_ST = T_5 - 1024;
constexpr int OFF_PHI = OFF_T + 4 * T_CH;
constexpr int OFF_EYE = OFF_PHI + 1024, OFF_ONE = OFF_EYE + 512;
constexpr int OFF_BAR = OFF_ONE + 256;
constexpr int SMEM_BYTES = OFF_BAR + 512 + 256 * DBG_TS;
constexpr uint32_t SB = 1024;
static_assert(T_KC + 2 * 656 <= T_CH, "table size");
static_assert(SMEM_BYTES <= 232448, "smem");
constexpr int MB_URAW = 0, MB_FULL = 1  , MB_WO = 17, MB_UFULL = 18, MB_OA = 19, MB_OB = 20, MB_OC = 21,
              MB_EMPTY = 22  , MB_AUX = 38;
__host__ __device__ constexpr uint32_t BAR(int i) { return SB + OFF_BAR + 8 * i; }
constexpr int NB_WG0 = 1, NB_ODONE = 2, NB_ST0 = 3  , NB_KV = 5, NB_YZ = 6, NB_INIT = 7, NB_PREP = 8, NB_PROD = 9, NB_KREAD = 10, NB_BDONE = 11, NB_ZERO = 12;
#define U_AT 2
#define ZERO_STEP 15
constexpr int SPIN_MAX = 1 << 16;

constexpr int X_CNT = 0;
constexpr int X_PART = 128;
constexpr int X_O = X_PART + 16 * 8 * 144;
constexpr int X_Y = X_O + 32 * 32 * 128;
constexpr int X_UT = X_Y + 512 * 8 * 32;
constexpr int X_SIZE = X_UT + 512 * (U_CH / 16);
__device__ __align__(128) uint4 g_x[X_SIZE];
extern __shared__ uint8_t smem_raw[];
#define TS(i) do {} while (0)
#define TS1(i) do {} while (0)
#define GT(i) do {} while (0)
#define TSDUMP(base) do {} while (0)

__device__ __forceinline__ uint32_t smem_u32(const void* p) { return (uint32_t)__cvta_generic_to_shared(p); }
__device__ __forceinline__ void mbar_arrive(uint32_t b) {
  asm volatile("mbarrier.arrive.shared::cta.b64 _, [%0];" ::"r"(b) : "memory");
}
__device__ __forceinline__ void mbar_wait(uint32_t b) {
  uint32_t done = 0;
#pragma unroll 1
  for (int i = 0; i < SPIN_MAX && !done; i++) {
    asm volatile("{\n.reg .pred p;\nmbarrier.try_wait.parity.shared::cta.b64 p, [%1], 0, 4000;\nselp.u32 %0, 1, 0, p;\n}\n"
                 : "=r"(done) : "r"(b) : "memory");
  }
}
__device__ __forceinline__ void mbar_spin(uint32_t b) {
  uint32_t done = 0;
#pragma unroll 1
  for (int i = 0; i < (SPIN_MAX << 4) && !done; i++) {
    asm volatile("{\n.reg .pred p;\nmbarrier.try_wait.parity.shared::cta.b64 p, [%1], 0;\nselp.u32 %0, 1, 0, p;\n}\n"
                 : "=r"(done) : "r"(b) : "memory");
  }
}
__device__ __forceinline__ void mbar_init(uint32_t b, int n) {
  asm volatile("mbarrier.init.shared::cta.b64 [%0], %1;" ::"r"(b), "r"(n) : "memory");
}
__device__ __forceinline__ void mbar_expect(uint32_t b, int bytes) {
  asm volatile("mbarrier.arrive.expect_tx.shared::cta.b64 _, [%0], %1;" ::"r"(b), "r"(bytes) : "memory");
}
__device__ __forceinline__ void nb_sync(int id, int n) { asm volatile("bar.sync %0, %1;" ::"r"(id), "r"(n) : "memory"); }
__device__ __forceinline__ void nb_arrive(int id, int n) { asm volatile("bar.arrive %0, %1;" ::"r"(id), "r"(n) : "memory"); }
#define ELECT "{\n.reg .pred p;\nelect.sync _|p, 0xffffffff;\n@p "
__device__ __forceinline__ void e_arrive(uint32_t b) {
  asm volatile(ELECT "mbarrier.arrive.shared::cta.b64 _, [%0];\n}\n" ::"r"(b) : "memory");
}
__device__ __forceinline__ void e_expect(uint32_t b, int bytes) {
  asm volatile(ELECT "mbarrier.arrive.expect_tx.shared::cta.b64 _, [%0], %1;\n}\n" ::"r"(b), "r"(bytes) : "memory");
}
__device__ __forceinline__ void e_tma2d(uint32_t dst, const CUtensorMap* m, uint32_t bar, int c0, int c1) {
  asm volatile(ELECT "cp.async.bulk.tensor.2d.shared::cluster.global.mbarrier::complete_tx::bytes [%0], [%1, {%3,%4}], [%2];\n}\n"
               ::"r"(dst), "l"(m), "r"(bar), "r"(c0), "r"(c1) : "memory");
}
__device__ __forceinline__ void e_tma3d(uint32_t dst, const CUtensorMap* m, uint32_t bar, int c0, int c1, int c2) {
  asm volatile(ELECT "cp.async.bulk.tensor.3d.shared::cluster.global.mbarrier::complete_tx::bytes [%0], [%1, {%3,%4,%5}], [%2];\n}\n"
               ::"r"(dst), "l"(m), "r"(bar), "r"(c0), "r"(c1), "r"(c2) : "memory");
}
__device__ __forceinline__ void e_tma4d(uint32_t dst, const CUtensorMap* m, uint32_t bar, int c0, int c3) {
  asm volatile(ELECT "cp.async.bulk.tensor.4d.shared::cluster.global.mbarrier::complete_tx::bytes [%0], [%1, {%3,%5,%5,%4}], [%2];\n}\n"
               ::"r"(dst), "l"(m), "r"(bar), "r"(c0), "r"(c3), "r"(0) : "memory");
}
__device__ __forceinline__ void e_bulk(uint32_t dst, const void* src, int bytes, uint32_t bar) {
  asm volatile(ELECT "cp.async.bulk.shared::cluster.global.mbarrier::complete_tx::bytes [%0], [%1], %2, [%3];\n}\n"
               ::"r"(dst), "l"(src), "r"(bytes), "r"(bar) : "memory");
}
__device__ __forceinline__ void e_prefetch(const void* p, int bytes) {
  asm volatile(ELECT "cp.async.bulk.prefetch.L2.global [%0], %1;\n}\n" ::"l"(p), "r"(bytes) : "memory");
}
__device__ __forceinline__ void e_store3d(const CUtensorMap* m, uint32_t src, int c1, int c2) {
  asm volatile(ELECT "cp.async.bulk.tensor.3d.global.shared::cta.bulk_group [%0, {%4,%2,%3}], [%1];\n"
               "@p cp.async.bulk.commit_group;\n@p cp.async.bulk.wait_group.read 0;\n}\n"
               ::"l"(m), "r"(src), "r"(c1), "r"(c2), "r"(0) : "memory");
}
__host__ __device__ constexpr uint64_t mkdesc(uint32_t addr, uint32_t lbo, uint32_t sbo, int swz) {
  return (uint64_t)((addr & 0x3FFFF) >> 4) | ((uint64_t)(lbo >> 4) << 16) | ((uint64_t)(sbo >> 4) << 32) |
         ((uint64_t)swz << 62);
}
#define SPLIT() asm volatile("{\n.reg .pred p;\nsetp.eq.u32 p, %0, %1;\n@p exit;\n}\n" ::"r"(blockIdx.y), "n"(__LINE__) : "memory")
#define WG_FENCE() asm volatile("wgmma.fence.sync.aligned;" ::: "memory")
#define WG_COMMIT() asm volatile("wgmma.commit_group.sync.aligned;" ::: "memory")
#define WG_WAIT(n) asm volatile("wgmma.wait_group.sync.aligned " #n ";" ::: "memory")

__device__ __forceinline__ void mma(float& d0, float& d1, float& d2, float& d3, uint32_t a0, uint32_t a1, uint32_t a2,
                                    uint32_t a3, uint32_t b0, uint32_t b1) {
  asm volatile("mma.sync.aligned.m16n8k16.row.col.f32.bf16.bf16.f32 {%0,%1,%2,%3},{%4,%5,%6,%7},{%8,%9},{%0,%1,%2,%3};"
               : "+f"(d0), "+f"(d1), "+f"(d2), "+f"(d3)
               : "r"(a0), "r"(a1), "r"(a2), "r"(a3), "r"(b0), "r"(b1));
}
__device__ __forceinline__ void mmac(float (&d)[4], uint32_t a0, uint32_t a1, uint32_t a2, uint32_t a3, uint32_t b0,
                                     uint32_t b1, const float (&c)[4]) {
  asm volatile("mma.sync.aligned.m16n8k16.row.col.f32.bf16.bf16.f32 {%0,%1,%2,%3},{%4,%5,%6,%7},{%8,%9},{%10,%11,%12,%13};"
               : "=f"(d[0]), "=f"(d[1]), "=f"(d[2]), "=f"(d[3])
               : "r"(a0), "r"(a1), "r"(a2), "r"(a3), "r"(b0), "r"(b1), "f"(c[0]), "f"(c[1]), "f"(c[2]), "f"(c[3]));
}
__device__ __forceinline__ void mma_p(int p, float (&d)[4], uint32_t a0, uint32_t a1, uint32_t a2, uint32_t a3, uint32_t b0, uint32_t b1) {
  asm volatile("{\n.reg .pred q;\nsetp.ne.b32 q, %10, 0;\n"
               "@q mma.sync.aligned.m16n8k16.row.col.f32.bf16.bf16.f32 {%0,%1,%2,%3},{%4,%5,%6,%7},{%8,%9},{%0,%1,%2,%3};\n}\n"
               : "+f"(d[0]), "+f"(d[1]), "+f"(d[2]), "+f"(d[3])
               : "r"(a0), "r"(a1), "r"(a2), "r"(a3), "r"(b0), "r"(b1), "r"(p));
}
__device__ __forceinline__ void mmac_p(int p, float (&d)[4], uint32_t a0, uint32_t a1, uint32_t a2, uint32_t a3, uint32_t b0,
                                       uint32_t b1, const float (&c)[4]) {
  asm volatile("{\n.reg .pred q;\nsetp.ne.b32 q, %14, 0;\n"
               "@q mma.sync.aligned.m16n8k16.row.col.f32.bf16.bf16.f32 {%0,%1,%2,%3},{%4,%5,%6,%7},{%8,%9},{%10,%11,%12,%13};\n}\n"
               : "+f"(d[0]), "+f"(d[1]), "+f"(d[2]), "+f"(d[3])
               : "r"(a0), "r"(a1), "r"(a2), "r"(a3), "r"(b0), "r"(b1), "f"(c[0]), "f"(c[1]), "f"(c[2]), "f"(c[3]), "r"(p));
}
__device__ __forceinline__ void mma_h(float (&d)[4], const uint32_t (&a)[4], uint32_t b0, uint32_t b1) {
  asm volatile("mma.sync.aligned.m16n8k16.row.col.f32.f16.f16.f32 {%0,%1,%2,%3},{%4,%5,%6,%7},{%8,%9},{%0,%1,%2,%3};"
               : "+f"(d[0]), "+f"(d[1]), "+f"(d[2]), "+f"(d[3]) : "r"(a[0]), "r"(a[1]), "r"(a[2]), "r"(a[3]), "r"(b0), "r"(b1));
}
__device__ __forceinline__ void mma0(float& d0, float& d1, float& d2, float& d3, uint32_t a0, uint32_t a1, uint32_t a2,
                                     uint32_t a3, uint32_t b0, uint32_t b1) {
  asm volatile("mma.sync.aligned.m16n8k16.row.col.f32.bf16.bf16.f32 {%0,%1,%2,%3},{%4,%5,%6,%7},{%8,%9},{%10,%10,%10,%10};"
               : "=f"(d0), "=f"(d1), "=f"(d2), "=f"(d3)
               : "r"(a0), "r"(a1), "r"(a2), "r"(a3), "r"(b0), "r"(b1), "f"(0.f));
}
__device__ __forceinline__ uint32_t pack_bf(float lo, float hi) {
  uint32_t r;
  asm("cvt.rn.bf16x2.f32 %0, %1, %2;" : "=r"(r) : "f"(hi), "f"(lo));
  return r;
}
__device__ __forceinline__ float bf_lo(uint32_t w) { return __uint_as_float(w << 16); }
__device__ __forceinline__ float bf_hi(uint32_t w) { return __uint_as_float(w & 0xffff0000u); }
__device__ __forceinline__ float bf_round(float x) { return __bfloat162float(__float2bfloat16_rn(x)); }
__device__ __forceinline__ uint32_t bmax2(uint32_t a, uint32_t b) {
  uint32_t r; asm("max.bf16x2 %0, %1, %2;" : "=r"(r) : "r"(a), "r"(b)); return r;
}
__device__ __forceinline__ uint32_t bmin2(uint32_t a, uint32_t b) {
  uint32_t r; asm("min.bf16x2 %0, %1, %2;" : "=r"(r) : "r"(a), "r"(b)); return r;
}
__device__ __forceinline__ float ex2(float x) { float r; asm("ex2.approx.ftz.f32 %0, %1;" : "=f"(r) : "f"(x)); return r; }
__device__ __forceinline__ float rcp(float x) { float r; asm("rcp.approx.ftz.f32 %0, %1;" : "=f"(r) : "f"(x)); return r; }
__device__ __forceinline__ void ldsm4(uint32_t (&r)[4], uint32_t a) {
  asm volatile("ldmatrix.sync.aligned.m8n8.x4.shared.b16 {%0,%1,%2,%3}, [%4];"
               : "=r"(r[0]), "=r"(r[1]), "=r"(r[2]), "=r"(r[3]) : "r"(a) : "memory");
}
__device__ __forceinline__ void ldsm4t(uint32_t (&r)[4], uint32_t a) {
  asm volatile("ldmatrix.sync.aligned.m8n8.x4.trans.shared.b16 {%0,%1,%2,%3}, [%4];"
               : "=r"(r[0]), "=r"(r[1]), "=r"(r[2]), "=r"(r[3]) : "r"(a) : "memory");
}
__device__ __forceinline__ void stsm4(uint32_t a, uint32_t r0, uint32_t r1, uint32_t r2, uint32_t r3) {
  asm volatile("stmatrix.sync.aligned.m8n8.x4.shared.b16 [%0], {%1,%2,%3,%4};"
               ::"r"(a), "r"(r0), "r"(r1), "r"(r2), "r"(r3) : "memory");
}
__device__ __forceinline__ uint32_t lds32(uint32_t a) {
  uint32_t r; asm volatile("ld.shared.u32 %0, [%1];" : "=r"(r) : "r"(a) : "memory"); return r;
}
__device__ __forceinline__ uint32_t lds16(uint32_t a) {
  uint32_t r; asm volatile("{\n.reg .u16 h;\nld.shared.u16 h, [%1];\ncvt.u32.u16 %0, h;\n}\n" : "=r"(r) : "r"(a) : "memory"); return r;
}
__device__ __forceinline__ uint2 lds64(uint32_t a) {
  uint2 r; asm volatile("ld.shared.v2.u32 {%0,%1}, [%2];" : "=r"(r.x), "=r"(r.y) : "r"(a) : "memory"); return r;
}
__device__ __forceinline__ uint4 lds128(uint32_t a) {
  uint4 r;
  asm volatile("ld.shared.v4.u32 {%0,%1,%2,%3}, [%4];" : "=r"(r.x), "=r"(r.y), "=r"(r.z), "=r"(r.w) : "r"(a) : "memory");
  return r;
}
__device__ __forceinline__ void sts32(uint32_t a, uint32_t v) { asm volatile("st.shared.u32 [%0], %1;" ::"r"(a), "r"(v) : "memory"); }
__device__ __forceinline__ void sts16(uint32_t a, uint32_t v) {
  asm volatile("{\n.reg .u16 h;\ncvt.u16.u32 h, %1;\nst.shared.u16 [%0], h;\n}\n" ::"r"(a), "r"(v) : "memory");
}
__device__ __forceinline__ void sts64(uint32_t a, uint32_t x, uint32_t y) {
  asm volatile("st.shared.v2.u32 [%0], {%1,%2};" ::"r"(a), "r"(x), "r"(y) : "memory");
}
__device__ __forceinline__ void sts128(uint32_t a, uint32_t x, uint32_t y, uint32_t z, uint32_t w) {
  asm volatile("st.shared.v4.u32 [%0], {%1,%2,%3,%4};" ::"r"(a), "r"(x), "r"(y), "r"(z), "r"(w) : "memory");
}
__device__ __forceinline__ uint4 ld_x(const uint4* p) {
  uint4 r;
  asm volatile("{\n.reg .b128 t;\nld.relaxed.gpu.global.b128 t, [%4];\nmov.b128 {%0,%1,%2,%3}, t;\n}\n"
               : "=r"(r.x), "=r"(r.y), "=r"(r.z), "=r"(r.w) : "l"(p) : "memory");
  return r;
}
__device__ __forceinline__ uint32_t ld_x32(const uint32_t* p) {
  uint32_t r; asm volatile("ld.relaxed.gpu.global.u32 %0, [%1];" : "=r"(r) : "l"(p) : "memory"); return r;
}
__device__ __forceinline__ void st_x(uint4* p, uint32_t x, uint32_t y, uint32_t z, uint32_t w) {
  asm volatile("{\n.reg .b128 t;\nmov.b128 t, {%1,%2,%3,%4};\nst.relaxed.gpu.global.b128 [%0], t;\n}\n"
               ::"l"(p), "r"(x), "r"(y), "r"(z), "r"(w) : "memory");
}
__device__ __forceinline__ void st_x_p(int p, uint4* a, uint32_t x, uint32_t y, uint32_t z, uint32_t w) {
  asm volatile("{\n.reg .b128 t;\n.reg .pred q;\nsetp.ne.b32 q, %5, 0;\nmov.b128 t, {%1,%2,%3,%4};\n@q st.relaxed.gpu.global.b128 [%0], t;\n}\n"
               ::"l"(a), "r"(x), "r"(y), "r"(z), "r"(w), "r"(p) : "memory");
}
__device__ __forceinline__ void sts64_p(int p, uint32_t a, uint32_t x, uint32_t y) {
  asm volatile("{\n.reg .pred q;\nsetp.ne.b32 q, %3, 0;\n@q st.shared.v2.u32 [%0], {%1,%2};\n}\n" ::"r"(a), "r"(x), "r"(y), "r"(p) : "memory");
}
__device__ __forceinline__ void st_x32(uint32_t* p, uint32_t x) {
  asm volatile("st.relaxed.gpu.global.u32 [%0], %1;" ::"l"(p), "r"(x) : "memory");
}
__device__ __forceinline__ uint32_t nz(uint32_t w) { return max(w, 1u); }
__device__ __forceinline__ uint32_t fu(float x) { return __float_as_uint(x); }
__device__ __forceinline__ float uf(uint32_t x) { return __uint_as_float(x); }

__device__ __forceinline__ void wgmma_ss_n96(float (&d)[48], uint64_t da, uint64_t db, int sc) {
  asm volatile("{\n.reg .pred p;\nsetp.ne.b32 p, %50, 0;\n"
      "wgmma.mma_async.sync.aligned.m64n96k16.f32.bf16.bf16 "
      "{%0,%1,%2,%3,%4,%5,%6,%7,%8,%9,%10,%11,%12,%13,%14,%15,%16,%17,%18,%19,%20,%21,%22,%23,%24,%25,%26,%27,%28,%29,%30,%31,%32,%33,%34,%35,%36,%37,%38,%39,%40,%41,%42,%43,%44,%45,%46,%47}, "
      "%48, %49, p, 1, 1, 0, 1;\n}\n"
      : "+f"(d[0]), "+f"(d[1]), "+f"(d[2]), "+f"(d[3]), "+f"(d[4]), "+f"(d[5]), "+f"(d[6]), "+f"(d[7]),
        "+f"(d[8]), "+f"(d[9]), "+f"(d[10]), "+f"(d[11]), "+f"(d[12]), "+f"(d[13]), "+f"(d[14]), "+f"(d[15]),
        "+f"(d[16]), "+f"(d[17]), "+f"(d[18]), "+f"(d[19]), "+f"(d[20]), "+f"(d[21]), "+f"(d[22]), "+f"(d[23]),
        "+f"(d[24]), "+f"(d[25]), "+f"(d[26]), "+f"(d[27]), "+f"(d[28]), "+f"(d[29]), "+f"(d[30]), "+f"(d[31]),
        "+f"(d[32]), "+f"(d[33]), "+f"(d[34]), "+f"(d[35]), "+f"(d[36]), "+f"(d[37]), "+f"(d[38]), "+f"(d[39]),
        "+f"(d[40]), "+f"(d[41]), "+f"(d[42]), "+f"(d[43]), "+f"(d[44]), "+f"(d[45]), "+f"(d[46]), "+f"(d[47])
      : "l"(da), "l"(db), "r"(sc));
}

__device__ __forceinline__ void wgmma_ss_n128(float (&d)[64], uint64_t da, uint64_t db, int sc) {
  asm volatile("{\n.reg .pred p;\nsetp.ne.b32 p, %66, 0;\n"
      "wgmma.mma_async.sync.aligned.m64n128k16.f32.bf16.bf16 "
      "{%0,%1,%2,%3,%4,%5,%6,%7,%8,%9,%10,%11,%12,%13,%14,%15,%16,%17,%18,%19,%20,%21,%22,%23,%24,%25,%26,%27,%28,%29,%30,%31,%32,%33,%34,%35,%36,%37,%38,%39,%40,%41,%42,%43,%44,%45,%46,%47,%48,%49,%50,%51,%52,%53,%54,%55,%56,%57,%58,%59,%60,%61,%62,%63}, "
      "%64, %65, p, 1, 1, 0, 1;\n}\n"
      : "+f"(d[0]), "+f"(d[1]), "+f"(d[2]), "+f"(d[3]), "+f"(d[4]), "+f"(d[5]), "+f"(d[6]), "+f"(d[7]),
        "+f"(d[8]), "+f"(d[9]), "+f"(d[10]), "+f"(d[11]), "+f"(d[12]), "+f"(d[13]), "+f"(d[14]), "+f"(d[15]),
        "+f"(d[16]), "+f"(d[17]), "+f"(d[18]), "+f"(d[19]), "+f"(d[20]), "+f"(d[21]), "+f"(d[22]), "+f"(d[23]),
        "+f"(d[24]), "+f"(d[25]), "+f"(d[26]), "+f"(d[27]), "+f"(d[28]), "+f"(d[29]), "+f"(d[30]), "+f"(d[31]),
        "+f"(d[32]), "+f"(d[33]), "+f"(d[34]), "+f"(d[35]), "+f"(d[36]), "+f"(d[37]), "+f"(d[38]), "+f"(d[39]),
        "+f"(d[40]), "+f"(d[41]), "+f"(d[42]), "+f"(d[43]), "+f"(d[44]), "+f"(d[45]), "+f"(d[46]), "+f"(d[47]),
        "+f"(d[48]), "+f"(d[49]), "+f"(d[50]), "+f"(d[51]), "+f"(d[52]), "+f"(d[53]), "+f"(d[54]), "+f"(d[55]),
        "+f"(d[56]), "+f"(d[57]), "+f"(d[58]), "+f"(d[59]), "+f"(d[60]), "+f"(d[61]), "+f"(d[62]), "+f"(d[63])
      : "l"(da), "l"(db), "r"(sc));
}

__device__ __forceinline__ void wgmma_ss_n40(float (&d)[20], uint64_t da, uint64_t db, int sc) {
  asm volatile("{\n.reg .pred p;\nsetp.ne.b32 p, %22, 0;\n"
      "wgmma.mma_async.sync.aligned.m64n40k16.f32.bf16.bf16 "
      "{%0,%1,%2,%3,%4,%5,%6,%7,%8,%9,%10,%11,%12,%13,%14,%15,%16,%17,%18,%19}, "
      "%20, %21, p, 1, 1, 1, 1;\n}\n"
      : "+f"(d[0]), "+f"(d[1]), "+f"(d[2]), "+f"(d[3]), "+f"(d[4]), "+f"(d[5]), "+f"(d[6]), "+f"(d[7]),
        "+f"(d[8]), "+f"(d[9]), "+f"(d[10]), "+f"(d[11]), "+f"(d[12]), "+f"(d[13]), "+f"(d[14]), "+f"(d[15]),
        "+f"(d[16]), "+f"(d[17]), "+f"(d[18]), "+f"(d[19])
      : "l"(da), "l"(db), "r"(sc));
}

__device__ __forceinline__ void wgmma_rs_n8(float (&d)[4], const uint4& a, uint64_t db, int sc) {
  asm volatile("{\n.reg .pred p;\nsetp.ne.b32 p, %9, 0;\n"
      "wgmma.mma_async.sync.aligned.m64n8k16.f32.bf16.bf16 "
      "{%0,%1,%2,%3}, "
      "{%4,%5,%6,%7}, %8, p, 1, 1, 1;\n}\n"
      : "+f"(d[0]), "+f"(d[1]), "+f"(d[2]), "+f"(d[3])
      : "r"(a.x), "r"(a.y), "r"(a.z), "r"(a.w), "l"(db), "r"(sc));
}

__device__ __forceinline__ void wgmma_rs_n16(float (&d)[8], const uint4& a, uint64_t db, int sc) {
  asm volatile("{\n.reg .pred p;\nsetp.ne.b32 p, %13, 0;\n"
      "wgmma.mma_async.sync.aligned.m64n16k16.f32.bf16.bf16 "
      "{%0,%1,%2,%3,%4,%5,%6,%7}, "
      "{%8,%9,%10,%11}, %12, p, 1, 1, 1;\n}\n"
      : "+f"(d[0]), "+f"(d[1]), "+f"(d[2]), "+f"(d[3]), "+f"(d[4]), "+f"(d[5]), "+f"(d[6]), "+f"(d[7])
      : "r"(a.x), "r"(a.y), "r"(a.z), "r"(a.w), "l"(db), "r"(sc));
}

__device__ __forceinline__ void wgmma_rs_n24(float (&d)[12], const uint4& a, uint64_t db, int sc) {
  asm volatile("{\n.reg .pred p;\nsetp.ne.b32 p, %17, 0;\n"
      "wgmma.mma_async.sync.aligned.m64n24k16.f32.bf16.bf16 "
      "{%0,%1,%2,%3,%4,%5,%6,%7,%8,%9,%10,%11}, "
      "{%12,%13,%14,%15}, %16, p, 1, 1, 1;\n}\n"
      : "+f"(d[0]), "+f"(d[1]), "+f"(d[2]), "+f"(d[3]), "+f"(d[4]), "+f"(d[5]), "+f"(d[6]), "+f"(d[7]),
        "+f"(d[8]), "+f"(d[9]), "+f"(d[10]), "+f"(d[11])
      : "r"(a.x), "r"(a.y), "r"(a.z), "r"(a.w), "l"(db), "r"(sc));
}

struct Params {
  const __nv_bfloat16 *logA, *Aim, *Cre, *Cim, *logdt, *Dskip, *x, *wphi, *wo;
  __nv_bfloat16* out;
  uint4* xs;
  long long* ts;
};

__device__ __forceinline__ uint4 tr_row(const uint4 (&v)[8], int i) {
  uint32_t o[4];
#pragma unroll
  for (int m = 0; m < 4; m++) {
    const uint4 &ra = v[2 * m], &rb = v[2 * m + 1];
    const int k = i >> 1;
    const uint32_t xa = k == 0 ? ra.x : k == 1 ? ra.y : k == 2 ? ra.z : ra.w;
    const uint32_t xb = k == 0 ? rb.x : k == 1 ? rb.y : k == 2 ? rb.z : rb.w;
    o[m] = __byte_perm(xa, xb, (i & 1) ? 0x7632 : 0x5410);
  }
  return make_uint4(o[0], o[1], o[2], o[3]);
}

struct cpx { float r, i; };
__device__ __forceinline__ cpx csq(cpx a) { return {a.r * a.r - a.i * a.i, 2.f * (a.r * a.i)}; }
__device__ __forceinline__ cpx polar(float e, float t) {
  const float m = ex2(e);
  return {m * __cosf(t), m * __sinf(t)};
}

struct KgenRaw { unsigned short la, ai, cr, ci, ldt; };
__device__ __forceinline__ KgenRaw kgen_load(const Params& P, int d, int unit, int lane) {
  const int o = d * 128 + unit * 32 + lane;
  return {__ldg((const unsigned short*)P.logA + o), __ldg((const unsigned short*)P.Aim + o), __ldg((const unsigned short*)P.Cre + o),
          __ldg((const unsigned short*)P.Cim + o), __ldg((const unsigned short*)P.logdt + d)};
}
struct hmul { __half2 a, b; };
__device__ __forceinline__ hmul mk_mul(cpx w) {
  uint32_t b;
  asm("{\n.reg .f32 n;\nneg.ftz.f32 n, %1;\ncvt.rn.f16x2.f32 %0, %2, n;\n}\n" : "=r"(b) : "f"(w.i), "f"(w.r));
  return {__floats2half2_rn(w.r, w.i), *(const __half2*)&b};
}
__device__ __forceinline__ __half2 hcm(__half2 z, const hmul& w) { return __hfma2(__high2half2(z), w.b, __hmul2(__low2half2(z), w.a)); }
__device__ __forceinline__ uint32_t hu(__half2 v) { return *(const uint32_t*)&v; }

struct KgenAddr { uint32_t sa, sb, lb, lc, la; };
__device__ __forceinline__ KgenAddr kgen_addr(int lane, uint32_t buf) {
  KgenAddr a;
  a.sa = buf + (lane & 7) * 128 + ((((lane >> 3) ^ lane) & 7) << 4);
  a.lb = buf + (lane >> 3) * 128 + (((lane ^ (lane >> 3)) & 7) << 4);
  a.la = buf + ((lane >> 3) & 1) * 1024 + (lane >> 4) * 128 + (((lane ^ (lane >> 4)) & 7) << 4);
  a.sb = a.sa ^ 64; a.lc = a.lb ^ 64;
  asm volatile("" : "+r"(a.sa), "+r"(a.sb), "+r"(a.lb), "+r"(a.lc), "+r"(a.la));
  return a;
}
__device__ __forceinline__ void kgen_unit(const KgenRaw& r, const KgenAddr& ad, uint32_t zero, float (&k)[5][4], float& k2048, float& sc) {
  const float dt = bf_round(expf(bf_lo(r.ldt)));
  const float a2 = bf_round(ex2(bf_lo(r.la) * 1.4426950408889634f)) * (dt * -1.4426950408889634f);
  const float f = bf_lo(r.ai) * dt;
  const float r128 = f * 20.371832715762604f;
  const uint32_t ex = min(max(__reduce_max_sync(0xffffffffu, max(r.cr & 0x7fffu, r.ci & 0x7fffu)) >> 7, 1u), 253u);
  const float cs = uf((254u - ex) << 23);
  sc = 2.f * dt * uf(ex << 23);
  const cpx C = {bf_lo(r.cr) * cs, -bf_lo(r.ci) * cs};
  auto put = [&](const __half2 (&v)[8], uint32_t off) {
    stsm4(ad.sa + off, hu(v[0]), hu(v[1]), hu(v[2]), hu(v[3]));
    stsm4(ad.sb + off, hu(v[4]), hu(v[5]), hu(v[6]), hu(v[7]));
  };
  uint32_t A[4][4], B[5][2][4];
  auto get = [&](int j, uint32_t off) {
    __syncwarp();
    ldsm4(B[j][0], ad.lb + off);
    ldsm4(B[j][1], ad.lc + 512 + off);
  };
  auto tile = [&](int j) {
    k[j][0] = k[j][1] = k[j][2] = k[j][3] = 0.f;
#pragma unroll
    for (int s = 0; s < 4; s++) mma_h(k[j], A[s], B[j][s >> 1][2 * (s & 1)], B[j][s >> 1][2 * (s & 1) + 1]);
  };
  auto after = [&](cpx v, uint32_t dep) { return cpx{uf(fu(v.r) ^ (dep & zero)), v.i}; };
  const cpx w1 = polar(a2, f), w128 = polar(a2 * 128.f, (r128 - rintf(r128)) * 6.283185307179586f);
  const cpx w2 = csq(w1), w4 = csq(w2);
  __half2 t0[8], t1[8], t2[8], t3[8], t4[8];
  const hmul m2 = mk_mul(w2), m4 = mk_mul(w4), m128 = mk_mul(w128);
  t0[0] = __floats2half2_rn(1.f, 0.f); t0[1] = __floats2half2_rn(w1.r, w1.i); t0[2] = m2.a; t0[4] = m4.a;
  t0[3] = hcm(t0[1], m2); t0[5] = hcm(t0[1], m4); t0[6] = hcm(t0[2], m4); t0[7] = hcm(t0[3], m4);
  put(t0, 0); get(0, 0);
  t1[0] = m128.a;
#pragma unroll
  for (int i = 1; i < 8; i++) t1[i] = hcm(t0[i], m128);
  put(t1, 1024); get(1, 1024);
  {
    cpx w8 = csq(after(w4, B[0][0][0]));
    w8.i = -w8.i;
    const cpx w16 = csq(w8), w32 = csq(w16), w64 = csq(w32);
    const hmul m8 = mk_mul(w8), m16 = mk_mul(w16), m32 = mk_mul(w32), m64 = mk_mul(w64);
    __half2 a[8];
    a[0] = __floats2half2_rn(C.r, C.i); a[1] = hcm(a[0], m8);
    a[2] = hcm(a[0], m16); a[3] = hcm(a[1], m16);
#pragma unroll
    for (int i = 0; i < 4; i++) a[4 + i] = hcm(a[i], m32);
    put(a, 0);
#pragma unroll
    for (int i = 0; i < 8; i++) a[i] = hcm(a[i], m64);
    put(a, 1024);
    __syncwarp();
#pragma unroll
    for (int s = 0; s < 4; s++) ldsm4(A[s], (ad.la ^ (s << 5)) + s * 256);
  }
  const cpx w256 = csq(after(w128, B[1][0][0]));
  const hmul m256 = mk_mul(w256);
  t2[0] = m256.a;
#pragma unroll
  for (int i = 1; i < 8; i++) t2[i] = hcm((i & 1) ? t1[i & 6] : t0[i & 6], m256);
  put(t2, 0); get(2, 0);
  tile(0); tile(1);
  const cpx w512 = csq(after(w256, A[0][0]));
  const hmul m512 = mk_mul(w512);
  t3[0] = m512.a;
#pragma unroll
  for (int i = 1; i < 8; i++) t3[i] = hcm((i & 2) ? t2[i & 5] : ((i & 1) ? t1[i & 4] : t0[i & 4]), m512);
  put(t3, 1024); get(3, 1024);
  tile(2);
  const cpx w1024 = csq(after(w512, B[2][0][0])), we = csq(w1024);
  const hmul m1024 = mk_mul(w1024);
  t4[0] = m1024.a;
#pragma unroll
  for (int i = 1; i < 8; i++) t4[i] = hcm((i & 4) ? t3[i & 3] : ((i & 2) ? t2[i & 1] : t1[0]), m1024);
  put(t4, 0); get(4, 0);
  tile(3); tile(4);
  k2048 = (C.r * we.r + C.i * we.i) * sc;
}

__device__ __forceinline__ void build_tables(uint32_t tb, int lane, float (&k)[5][4], float k2048) {
  const int g = lane >> 2, c = lane & 3;
  const uint32_t kc = tb + T_KC + 16;
  {
    const uint32_t a0 = kc + 16 * g + 4 * c, a2 = kc + 2 * (256 + 4 * g + c);
    const uint32_t a3 = kc + 2 * (384 + 2 * g + 64 * (c & 1) + (c >> 1)), a4 = kc + 2 * (512 + g + 32 * c);
#pragma unroll
    for (int r = 0; r < 2; r++) {
      sts32(a0 + 128 * r, pack_bf(k[0][2 * r], k[0][2 * r + 1]));
      sts32(a0 + 128 * r + 256, pack_bf(k[1][2 * r], k[1][2 * r + 1]));
      const uint32_t w2 = pack_bf(k[2][2 * r], k[2][2 * r + 1]);
      const uint32_t w3 = pack_bf(k[3][2 * r], k[3][2 * r + 1]);
      const uint32_t w4 = pack_bf(k[4][2 * r], k[4][2 * r + 1]);
      sts16(a2 + 64 * r, w2); sts16(a2 + 64 * r + 128, w2 >> 16);
      sts16(a3 + 32 * r, w3); sts16(a3 + 32 * r + 64, w3 >> 16);
      sts16(a4 + 16 * r, w4); sts16(a4 + 16 * r + 32, w4 >> 16);
    }
  }
  if (lane == 0) { sts16(kc + 2 * 640, pack_bf(k2048, 0.f)); sts32(kc - 4, 0); }
  __syncwarp();
  const uint32_t td = tb + T_D + 32;
#pragma unroll
  for (int hf = 0; hf < 2; hf++) {
    const uint2 v = lds64(kc + 256 * hf + 8 * lane);
    const uint32_t pv = lds32(kc + 256 * hf + 8 * lane - 4);
    sts128(td + 512 * hf + 16 * lane, __byte_perm(v.x, pv, 0x7610), __byte_perm(v.x, v.x, 0x1032), __byte_perm(v.y, v.x, 0x7610),
           __byte_perm(v.y, v.y, 0x1032));
  }
#pragma unroll
  for (int hf = 0; hf < 2; hf++) {
    const uint32_t v = lds32(kc + 512 + 128 * hf + 4 * lane), nx = lds32(kc + 516 + 128 * hf + 4 * lane);
    uint32_t w0 = __byte_perm(v, v, 0x1010);
    const uint32_t w1 = w0;
    if (hf == 0) { const uint32_t pv = lds32(kc + 508); if (lane == 0) w0 = __byte_perm(v, pv, 0x7610); }
    sts128(td + 1024 + 512 * hf + 16 * lane, w0, w1, __byte_perm(v, v, 0x1032), __byte_perm(nx, v, 0x7610));
  }
  {
    const uint32_t kk = lds16(kc + 2 * 384);
    const uint32_t w = lane < 3 ? (kk | (kk << 16)) : (lane == 3 ? (kk << 16) : 0u);
    if (lane < 24) sts32(td + 4 * (lane < 16 ? 512 + lane : lane - 24), w);
    const uint32_t lo_ = lds16(kc + 2 * 511), le_ = lds16(kc + 2 * 512);
    const uint32_t ja = tb + T_5 + (lane < 16 ? 4 * lane : 256 + 4 * lane);
    sts32(ja, lane == 16 ? (le_ << 16) : 0u);
    sts32(ja + 384, lane == 16 ? (lo_ << 16) : 0u);
    sts32(tb + (lane < 16 ? T_7 : T_9 - 64) + 4 * lane, 0u);
  }
#pragma unroll
  for (int s = 0; s < 2; s++) {
    const uint32_t b = kc + 2 * (s ? 512 : 384) + 8 * lane;
    const uint2 v = lds64(b);
    uint32_t em = lds16(b - 2), e0 = v.x;
    const uint32_t e4 = lds16(b + 8);
    if (lane == 0) { em = 0; e0 = 0; }
    sts64(tb + (s ? T_7 : T_3) + 64 + 8 * lane, __byte_perm(v.x, em, 0x5432), __byte_perm(v.y, v.x, 0x7632));
    sts64(tb + (s ? T_9 : T_5) + 64 + 8 * lane, __byte_perm(v.y, e0, 0x5410), __byte_perm(e4, v.y, 0x5410));
  }
  __syncwarp();
}

__device__ __forceinline__ uint32_t box2w(int lo, int n, int o) {
  return ((unsigned)(o - lo) < (unsigned)n ? 0x3F80u : 0u) | ((unsigned)(o + 1 - lo) < (unsigned)n ? 0x3F800000u : 0u);
}

__device__ __forceinline__ void conv_channel(uint32_t ub, uint32_t tb, int lane, uint4* ydst) {
  const int g = lane >> 2, c = lane & 3, x = g - 2 * c;
  const int mi = lane >> 3;
  const uint32_t qa = ub + U_PAD + 16 * (lane & 7) + ((mi == 0 || mi == 3) ? U_ODD : 0) - (mi == 0 ? 16 : 0);
  const uint32_t hb = ub + U_PAD + (mi & 1) * U_ODD + 16 * ((lane >> 4) + (lane & 7)) - 16;
  const uint32_t kv = lds16(tb + T_KC + 16 + 2 * 512);
  const int oh = c < 2 ? 8 + 2 * c : 2 * c - 8, og = c < 3 ? 2 * c : -10;
  uint32_t bx[4] = {box2w(g - 4, 9, 2 * c), box2w(g - 3, 7, 2 * c), box2w(g - 4, 9, oh), box2w(g - 3, 7, oh)};
  uint32_t by[4] = {box2w(g - 10, 5, 2 * c - 8), box2w(g - 5, 3, 2 * c - 8), box2w(g - 10, 5, og), box2w(g - 5, 3, og)};
  uint32_t lb0 = ((unsigned)(x + 5) < 2u ? kv : 0u) | ((unsigned)(x + 4) < 2u ? kv << 16 : 0u);
  uint32_t lb1 = ((unsigned)(x - 3) < 2u ? kv : 0u) | ((unsigned)(x - 4) < 2u ? kv << 16 : 0u);
  const int q0 = g - 1, q1 = c < 3 ? g : g - 2;
  uint32_t y0a = ub + U_PAD + (q0 & 1) * U_ODD + 16 * (q0 >> 1) + 4 * c;
  uint32_t y1a = ub + U_PAD + (q1 & 1) * U_ODD + 16 * (q1 >> 1) + 4 * c;
#pragma unroll
  for (int i = 0; i < 4; i++) asm volatile("" : "+r"(bx[i]), "+r"(by[i]));
  asm volatile("" : "+r"(lb0), "+r"(lb1), "+r"(y0a), "+r"(y1a));
  mbar_wait(BAR(MB_UFULL));
  mbar_wait(BAR(MB_EMPTY + 15));
  TS(36);
  float acc[16][4];
  {
    uint32_t z09[8], z07[8], zm9[8], zm7[8];
#pragma unroll
    for (int i = 0; i < 8; i++) {
      uint32_t h[4];
      ldsm4(h, hb + 128 * i);
      float y0, y1, y2, y3, w0, w1, w2, w3;
      mma0(y0, y1, y2, y3, bx[0], bx[1], bx[2], bx[3], h[2], c < 2 ? h[3] : h[1]);
      mma0(w0, w1, w2, w3, bx[0], bx[1], bx[2], bx[3], h[1], c < 2 ? h[2] : h[0]);
      z09[i] = pack_bf(y0, y1); z07[i] = pack_bf(y2, y3);
      zm9[i] = pack_bf(w0, w1); zm7[i] = pack_bf(w2, w3);
    }
  uint32_t f3[3][4][4];
  {
    const uint32_t fa = tb + T_7 + 4 * (16 + x);
#pragma unroll
    for (int tt = 0; tt < 3; tt++)
#pragma unroll
      for (int D = 0; D < 4; D++) {
        const uint32_t a = fa + (tt == 0 ? 316 : (tt == 1 ? 320 : 0)) + 64 * D;
        f3[tt][D][0] = lds32(a); f3[tt][D][1] = lds32(a + 32); f3[tt][D][2] = lds32(a - 32); f3[tt][D][3] = lds32(a);
      }
  }
    float a[4][2][4];
#pragma unroll
    for (int kap = 0; kap < 4; kap++)
#pragma unroll
      for (int sg = 0; sg < 2; sg++)
#pragma unroll
        for (int bk = 3; bk >= kap; bk--) {
          const uint32_t(&q0_)[4] = f3[sg ? 2 : 0][bk - kap];
          const uint32_t(&q1_)[4] = f3[sg ? 2 : 1][bk - kap];
          float(&a0)[4] = a[bk][0];
          float(&a1)[4] = a[bk][1];
          if (sg == 0 && kap == 0) {
            mma0(a0[0], a0[1], a0[2], a0[3], q0_[0], q0_[1], q0_[2], q0_[3], z09[0], z09[1]);
            mma0(a1[0], a1[1], a1[2], a1[3], q1_[0], q1_[1], q1_[2], q1_[3], zm9[0], zm9[1]);
          } else {
            mma(a0[0], a0[1], a0[2], a0[3], q0_[0], q0_[1], q0_[2], q0_[3], sg ? zm7[2 * kap] : z09[2 * kap], sg ? zm7[2 * kap + 1] : z09[2 * kap + 1]);
            mma(a1[0], a1[1], a1[2], a1[3], q1_[0], q1_[1], q1_[2], q1_[3], sg ? z07[2 * kap] : zm9[2 * kap], sg ? z07[2 * kap + 1] : zm9[2 * kap + 1]);
          }
        }
    SPLIT();
#pragma unroll
    for (int i = 0; i < 8; i++) {
      uint32_t h[4];
      ldsm4(h, qa + 128 * i);
      const float ci[4] = {a[i >> 1][0][2 * (i & 1)], a[i >> 1][0][2 * (i & 1) + 1], a[i >> 1][1][2 * (i & 1)], a[i >> 1][1][2 * (i & 1) + 1]};
      mmac(acc[8 + i], h[0], h[1], h[2], h[3], lb0, lb1, ci);
    }
  }
  TS(44);
  {
    uint2 a5[10], a3[10];
    const uint32_t aa = tb + T_5 + 4 * (8 + 2 * g - 2 * c);
#pragma unroll
    for (int m = 0; m < 10; m++) { a5[m] = lds64(aa + 32 * m); a3[m] = lds64(aa + 384 + 32 * m); }
    uint32_t x5[12][2], x3[12][2];
    auto ygen = [&](int kap) {
#pragma unroll
      for (int hh = 0; hh < 2; hh++) {
        float y0, y1, y2, y3;
        mma0(y0, y1, y2, y3, by[0], by[1], by[2], by[3], lds32(y0a + 128 * kap + 64 * hh), lds32(y1a + 128 * kap + 64 * hh));
        x5[kap][hh] = pack_bf(y0, y1);
        x3[kap][hh] = pack_bf(y2, y3);
      }
    };
    ygen(11); ygen(10); ygen(9); ygen(8);
#pragma unroll
    for (int kap = 11; kap >= 0; kap--) {
      if (kap >= 4) ygen(kap - 4);
#pragma unroll
      for (int sg = 0; sg < 2; sg++)
#pragma unroll
        for (int i = 4; i >= 0; i--) {
          const int be = kap + 4 + i;
          if (be <= 15) {
            const uint2 &hi = sg ? a3[2 * i + 1] : a5[2 * i + 1], &lo = sg ? a3[2 * i] : a5[2 * i];
            const uint32_t b0 = sg ? x3[kap][0] : x5[kap][0], b1 = sg ? x3[kap][1] : x5[kap][1];
            if (be < 8 && i == 0 && sg == 0) mma0(acc[be][0], acc[be][1], acc[be][2], acc[be][3], hi.x, hi.y, lo.x, lo.y, b0, b1);
            else mma(acc[be][0], acc[be][1], acc[be][2], acc[be][3], hi.x, hi.y, lo.x, lo.y, b0, b1);
          }
        }
    }
  }
  TS(45);
  {
    const uint32_t st = tb + T_ST + lane * 8;
#pragma unroll
    for (int be = 4; be < 12; be++) sts64(st + 256 * be, pack_bf(acc[be][0], acc[be][1]), pack_bf(acc[be][2], acc[be][3]));
    SPLIT();
    uint32_t F[66], qd[8][4];
    const uint32_t fa = tb + T_D + 32 + 4 * x;
#pragma unroll
    for (int i = 0; i < 32; i++) {
      const int s = 120 - (i >> 2) - 8 * (i & 3);
      uint32_t(&q)[4] = qd[i & 7];
      ldsm4(q, qa + 16 * s);
      const int m = 16 * (i & 3) + 2 * (i >> 2);
      F[m] = lds32(fa + 32 * m); F[m + 1] = lds32(fa + 32 * m + 32);
#pragma unroll
      for (int be = 15; be >= 12; be--) {
        const int de = 8 * be - s;
        if (de >= 0) mma(acc[be][0], acc[be][1], acc[be][2], acc[be][3], q[0], q[1], q[2], q[3], F[2 * de + 1], F[2 * de]);
      }
    }
    F[64] = lds32(fa + 32 * 64); F[65] = lds32(fa + 32 * 65);
    uint32_t qp = qa + 128 * 11, sta = st + 256 * 10;
    uint4* yd = ydst + 7 * 32;
#pragma unroll
    for (int i = 0; i < 6; i++) ldsm4(qd[i], qp - 16 * i);
    uint2 sv = lds64(sta + 256);
    float ci[4] = {bf_lo(sv.x), bf_hi(sv.x), bf_lo(sv.y), bf_hi(sv.y)};
    float T[5][4];
#pragma unroll
    for (int i = 0; i < 16; i++) T[i >> 2][i & 3] = acc[12 + (i >> 2)][i & 3];
    nb_sync(NB_YZ, 160);
    TS(46);
#pragma unroll 1
    for (int bp = 5; bp >= 0; bp--) {
      uint32_t held[2];
#pragma unroll
      for (int o = 1; o >= 0; o--) {
#pragma unroll
        for (int k = 4; k >= 1; k--) mmac(T[k], qd[0][0], qd[0][1], qd[0][2], qd[0][3], F[16 * k + 1], F[16 * k], T[k - 1]);
        mmac(T[0], qd[0][0], qd[0][1], qd[0][2], qd[0][3], F[1], F[0], ci);
        ldsm4(qd[6], qp - 16 * 6);
        ldsm4(qd[7], qp - 16 * 7);
        sv = lds64(sta);
#pragma unroll
        for (int i = 1; i < 8; i++) {
#pragma unroll
          for (int k = 3; k >= 0; k--)
            mma(T[k][0], T[k][1], T[k][2], T[k][3], qd[i][0], qd[i][1], qd[i][2], qd[i][3], F[16 * k + 2 * i + 1], F[16 * k + 2 * i]);
          if (i < 7) ldsm4(qd[i - 1], qp - 128 - 16 * (i - 1));
          if (i == 2) {
            const uint32_t w0 = pack_bf(T[4][0], T[4][1]), w1 = pack_bf(T[4][2], T[4][3]);
            if (o) { held[0] = w0; held[1] = w1; }
            else st_x(yd, nz(w0), w1, held[0], held[1]);
          }
          if (i == 4) {
            if (2 * bp + o <= 4) sv = make_uint2(0, 0);
            ci[0] = bf_lo(sv.x); ci[1] = bf_hi(sv.x); ci[2] = bf_lo(sv.y); ci[3] = bf_hi(sv.y);
          }
        }
        qp -= 128; sta -= 256;
      }
      yd -= 32;
    }
#pragma unroll
    for (int B = 1; B >= 0; B--)
      st_x(ydst + B * 32, nz(pack_bf(T[2 * B][0], T[2 * B][1])), pack_bf(T[2 * B][2], T[2 * B][3]),
           pack_bf(T[2 * B + 1][0], T[2 * B + 1][1]), pack_bf(T[2 * B + 1][2], T[2 * B + 1][3]));
  }
}

__device__ __forceinline__ void dual_exp(const uint32_t* w, uint32_t* e) {
  const float L = 1.44268798828125f;
  uint32_t mx = bmax2(bmax2(w[0], w[1]), bmax2(w[2], w[3]));
  uint32_t mn = bmin2(bmin2(w[0], w[1]), bmin2(w[2], w[3]));
  mx = bmax2(mx, __shfl_xor_sync(0xffffffffu, mx, 1));
  mn = bmin2(mn, __shfl_xor_sync(0xffffffffu, mn, 1));
  mx = bmax2(mx, __shfl_xor_sync(0xffffffffu, mx, 2));
  mn = bmin2(mn, __shfl_xor_sync(0xffffffffu, mn, 2));
  const float mx0 = bf_lo(mx) * -L, mx1 = bf_hi(mx) * -L, mn0 = bf_lo(mn) * L, mn1 = bf_hi(mn) * L;
#pragma unroll
  for (int i = 0; i < 2; i++) {
    const float a0 = bf_lo(w[2 * i]), a1 = bf_hi(w[2 * i]), b0 = bf_lo(w[2 * i + 1]), b1 = bf_hi(w[2 * i + 1]);
    e[2 * i] = pack_bf(ex2(fmaf(a0, L, mx0)), ex2(fmaf(b0, L, mx0)));
    e[2 * i + 1] = pack_bf(ex2(fmaf(a1, L, mx1)), ex2(fmaf(b1, L, mx1)));
    e[4 + 2 * i] = pack_bf(ex2(fmaf(a0, -L, mn0)), ex2(fmaf(b0, -L, mn0)));
    e[5 + 2 * i] = pack_bf(ex2(fmaf(a1, -L, mn1)), ex2(fmaf(b1, -L, mn1)));
  }
}
__device__ __forceinline__ void normalise(uint32_t* e, const float (&s)[4]) {
  const uint32_t r = pack_bf(rcp(s[0]), rcp(s[2]));
  const __nv_bfloat162 rr = *(const __nv_bfloat162*)&r;
#pragma unroll
  for (int i = 0; i < 4; i++) {
    const __nv_bfloat162 v = __hmul2(*(const __nv_bfloat162*)&e[i], (i & 1) ? __high2bfloat162(rr) : __low2bfloat162(rr));
    e[i] = *(const uint32_t*)&v;
  }
}
__host__ __device__ constexpr uint64_t qdesc(uint32_t addr) { return mkdesc(addr, 128, 256, 0); }

__global__ void __launch_bounds__(NTHREADS, 1)
fused_kernel(const Params P, const __grid_constant__ CUtensorMap mx, const __grid_constant__ CUtensorMap mw,
             const __grid_constant__ CUtensorMap mo, const __grid_constant__ CUtensorMap mu,
             const __grid_constant__ CUtensorMap mout, const __grid_constant__ CUtensorMap mw4) {
  constexpr uint32_t sb = SB;
  const int tid = threadIdx.x, lane = tid & 31;
  const int warp = __shfl_sync(0xffffffffu, tid >> 5, 0);
  const int b = blockIdx.x, oct = b >> 3, i8 = b & 7;
  const int rt = oct < 8 ? oct : 15 - oct;
  const int hp = (oct >> 3) * 8 + i8;

  const int wg = warp >> 2, w = warp & 3;
  const int d = b * 4 + ((tid >> 5) & 3);
  if (tid < 384) {
    asm volatile("prefetch.tensormap [%0];" ::"l"(&mu) : "memory");
    asm volatile("prefetch.tensormap [%0];" ::"l"(&mw) : "memory");
    asm volatile("prefetch.tensormap [%0];" ::"l"(&mx) : "memory");
    asm volatile("prefetch.tensormap [%0];" ::"l"(&mw4) : "memory");
  }
  if (warp == 12) {
    if (lane == 0) {
#pragma unroll
      for (int i = 0; i < 9; i++) mbar_init(BAR(i), 1);
      asm volatile("fence.mbarrier_init.release.cluster;" ::: "memory");
    }
    __syncwarp();
    if (lane < 9) mbar_expect(BAR(0) + 8 * lane, lane == 5 ? 65536 : ((lane == 0 || lane > 5) ? 16384 : 28672));
    __syncwarp();
    e_tma3d(sb + OFF_W, &mw, BAR(MB_FULL), hp * 32, 0, 0);
    e_tma2d(sb + OFF_X + 3 * 16384, &mx, BAR(MB_FULL), 0, rt * 256);
    nb_arrive(NB_PROD, 192);
  } else if (warp == 13) {
    if (lane == 0) {
#pragma unroll
      for (int i = 9; i < 39; i++) mbar_init(BAR(i), i < MB_EMPTY ? 1 : (i < MB_AUX ? 4 : 8));
      asm volatile("fence.mbarrier_init.release.cluster;" ::: "memory");
    }
    __syncwarp();
    if (lane < 9) mbar_expect(BAR(MB_FULL + 8) + 8 * lane, lane < 8 ? 16384 : 131072);
    nb_arrive(NB_PROD, 192);
  }
  const KgenRaw raw = kgen_load(P, d, tid >> 7, lane);
  const unsigned short dsk = __ldg((const unsigned short*)P.Dskip + d);
  const uint32_t tb = sb + OFF_T + w * T_CH;
  const uint32_t kp = wg >= 2 ? sb + OFF_STG0 + 16384 + w * 2048 : ((tb + 127) & ~127u) + wg * 2048;
  const KgenAddr kad = kgen_addr(lane, wg == 3 ? sb + OFF_X + 32768 + w * 2048 : kp);
  if (wg == 1) nb_sync(NB_PROD, 192);
  if (warp == 12) {
#pragma unroll 1
    for (int kb = 1; kb < 4; kb++) {
      if (kb == U_AT) e_tma4d(sb + OFF_STG0, &mu, BAR(MB_URAW), i8 * 64, oct * 2);
      e_tma3d(sb + OFF_W + kb * 12288, &mw, BAR(MB_FULL) + 8 * kb, hp * 32, kb * 64, 0);
      e_tma2d(sb + OFF_X + (kb < 2 ? kb + 3 : kb - 2) * 16384, &mx, BAR(MB_FULL) + 8 * kb, kb * 64, rt * 256);
    }
    e_prefetch(P.x + (size_t)(rt * 256 + hp * 16) * 512, 16384);
    e_tma4d(sb + OFF_W + 4 * 12288, &mw4, BAR(MB_FULL + 4), hp * 32, 4);
    if (smem_u32(smem_raw) != SB) __trap();
    if (lane == 0) TS1(54);
  }
  float k[5][4], k2048, ksc;
  kgen_unit(raw, kad, blockIdx.y, k, k2048, ksc);
  TS(40 + wg);
  if ((fu(k[0][0]) & fu(k[1][0]) & fu(k[2][0]) & fu(k[3][0]) & fu(k[4][0])) == 0xffffffffu) sts32(kp, 0);
  if (wg == 3) {
    nb_sync(0, 512);
    if (warp == 12) {
      asm volatile("fence.proxy.async.shared::cta;" ::: "memory");
      e_tma2d(sb + OFF_X + 2 * 16384, &mx, BAR(MB_FULL + 4), 256, rt * 256);
    }
  } else if (wg) {
    nb_arrive(0, 512);
  }
  k2048 += __shfl_xor_sync(0xffffffffu, k2048, 16);
  k2048 += __shfl_xor_sync(0xffffffffu, k2048, 8);
  if (wg != 2) {
    uint32_t h[10];
#pragma unroll
    for (int j = 0; j < 10; j++) h[j] = hu(__floats2half2_rn(k[j >> 1][2 * (j & 1)], k[j >> 1][2 * (j & 1) + 1]));
    sts128(kp + lane * 16, h[0], h[1], h[2], h[3]);
    sts128(kp + 512 + lane * 16, h[4], h[5], h[6], h[7]);
    sts128(kp + 1024 + lane * 16, h[8], h[9], fu(k2048), fu(ksc));
  }
  if (wg == 0) { nb_arrive(NB_PREP, 512); nb_sync(0, 512); }
  else if (wg != 2) nb_arrive(NB_PREP, 512);
  else nb_sync(NB_PREP, 512);
  if (warp >= 12) {
    asm volatile("setmaxnreg.dec.sync.aligned.u32 32;");
    if (warp == 12) {
      uint32_t slot = sb + OFF_X + 3 * 16384;
#pragma unroll 1
      for (int n = 0; n < 11; n++) {
        mbar_spin(BAR(MB_EMPTY) + 8 * n);
        const int m = n + 5;
        e_tma2d(slot, &mx, BAR(MB_FULL) + 8 * m, (m & 7) * 64, rt * 256 + (m >> 3) * 128);
        slot = slot == sb + OFF_X + 4 * 16384 ? sb + OFF_X : slot + 16384;
        if (n == 7) e_prefetch(P.wo + (size_t)b * 2048, 4096);
      }
#pragma unroll 1
      for (int i = 0; i < 8; i++) {
        mbar_wait(BAR(MB_EMPTY + 10) + 8 * ((0x54332100u >> (4 * i)) & 7));
        const int w0 = (0x54736210u >> (4 * i)) & 7;
        e_tma3d(sb + OFF_W + w0 * 16384, &mo, BAR(MB_WO), 0, w0 * 64, (hp & 3) * 2);
      }
    } else {
      if (warp == 15) {
        const uint4 v0 = __ldg((const uint4*)P.wphi + hp * 64 + lane), v1 = __ldg((const uint4*)P.wphi + hp * 64 + 32 + lane);
        sts128(sb + OFF_PHI + (lane & 1) * 256 + (lane >> 1) * 16, v0.x, v0.y, v0.z, v0.w);
        sts128(sb + OFF_PHI + 512 + (lane & 1) * 256 + (lane >> 1) * 16, v1.x, v1.y, v1.z, v1.w);
        const uint32_t one = (((lane >> 3) ^ (lane >> 4)) & 1) ? 0u : ((lane & 1) ? 0x3F800000u : 0x3F80u);
        const int q = (lane >> 1) & 3;
        sts128(sb + OFF_EYE + lane * 16, q == 0 ? one : 0u, q == 1 ? one : 0u, q == 2 ? one : 0u, q == 3 ? one : 0u);
        sts64(sb + OFF_ONE + lane * 8, 0x3F803F80u, 0x3F803F80u);
        asm volatile("fence.proxy.async.shared::cta;" ::: "memory");
        nb_arrive(NB_KREAD, 160);
        mbar_wait(BAR(MB_EMPTY + ZERO_STEP));
        uint4* py = P.xs + X_Y + b * 1024 + lane;
#pragma unroll 1
        for (int i = 0; i < 1024; i += 32) st_x(py + i, 0, 0, 0, 0);
        nb_arrive(NB_YZ, 160);
        nb_arrive(NB_ODONE, 320);
        if (lane == 0) TS1(55);
        return;
      }
      uint32_t* const cnt = (uint32_t*)(P.xs + X_CNT) + (warp == 13 ? i8 : 8 + rt) * 32;
      const unsigned target = (ld_x32(cnt) & ~15u) + 16;
      if (warp == 13) {
        uint4* pp = P.xs + X_PART + (hp * 8 + rt) * 144 + lane;
#pragma unroll 1
        for (int i = 0; i < 144; i += 32) if (i + lane < 144) st_x(pp + i, 0, 0, 0, 0);
      }
      nb_sync(warp == 13 ? NB_INIT : NB_ODONE, warp == 13 ? 160 : 320);
      if (lane == 0) TS1(warp == 13 ? 49 : 56);
      asm volatile("fence.proxy.async.shared::cta;" ::: "memory");
      if (lane == 0) asm volatile("red.release.gpu.global.add.u32 [%0], 1;" ::"l"(cnt) : "memory");
      if (lane == 0) TS1(warp == 13 ? 50 : 57);
      const uint32_t* pc = (warp == 13 && (lane & 1)) ? (uint32_t*)(P.xs + X_CNT) + (b >> 4) * 32 : cnt;
#pragma unroll 1
      for (int i = 0; i < SPIN_MAX; i++) {
        unsigned v;
        asm volatile("ld.acquire.gpu.global.u32 %0, [%1];" : "=r"(v) : "l"(pc) : "memory");
        if (__all_sync(0xffffffffu, (int)(v - target) >= 0)) break;
      }
      if (lane == 0) TS1(warp == 13 ? 51 : 58);
      asm volatile("fence.proxy.async.global;" ::: "memory");
      if (warp == 13) {
        mbar_wait(BAR(MB_EMPTY + 11));
        e_expect(BAR(MB_UFULL), 4 * U_CH);
        e_bulk(sb + OFF_U, P.xs + X_UT + b * (U_CH / 4), 4 * U_CH, BAR(MB_UFULL));
      } else {
        const uint4* src = P.xs + X_O + (rt * 4 + (hp >> 2)) * 4096;
        e_expect(BAR(MB_OA), 14336);
        e_bulk(sb + OFF_STG0, src + 3200, 14336, BAR(MB_OA));
        e_expect(BAR(MB_OC), 32768);
        e_bulk(sb + OFF_X + 32768, src, 32768, BAR(MB_OC));
        nb_sync(NB_BDONE, 288);
        asm volatile("fence.proxy.async.shared::cta;" ::: "memory");
        e_expect(BAR(MB_OB), 18432);
        e_bulk(sb + OFF_U, src + 2048, 18432, BAR(MB_OB));
      }
    }
    return;
  }

  const int t = tid & 127;
  const int g = lane >> 2, c = lane & 3;
  {
    if (wg == 2) {
      asm volatile("setmaxnreg.inc.sync.aligned.u32 160;");
#pragma unroll
      for (int j = 0; j < 5; j++) { k[j][0] *= ksc; k[j][1] *= ksc; k[j][2] *= ksc; k[j][3] *= ksc; }
#pragma unroll 1
      for (int q = 0; q < 3; q++) {
        const uint32_t src = (q == 2 ? kp : ((tb + 127) & ~127u) + q * 2048) + lane * 16;
        const uint4 v0 = lds128(src), v1 = lds128(src + 512), v2 = lds128(src + 1024);
        const uint32_t h[10] = {v0.x, v0.y, v0.z, v0.w, v1.x, v1.y, v1.z, v1.w, v2.x, v2.y};
#pragma unroll
        for (int j = 0; j < 10; j++) {
          const float2 f = __half22float2(*(const __half2*)&h[j]);
          k[j >> 1][2 * (j & 1)] = fmaf(f.x, uf(v2.w), k[j >> 1][2 * (j & 1)]);
          k[j >> 1][2 * (j & 1) + 1] = fmaf(f.y, uf(v2.w), k[j >> 1][2 * (j & 1) + 1]);
        }
        k2048 += uf(v2.z);
      }
#pragma unroll
      for (int o2 = 4; o2; o2 >>= 1) k2048 += __shfl_xor_sync(0xffffffffu, k2048, o2);
      if (lane == 0) k[0][0] += bf_lo(dsk);
      __syncwarp();
      if (lane == 0) mbar_arrive(BAR(MB_AUX));
      TS(34);
      build_tables(tb, lane, k, k2048);
      TS(35);
      uint4* const g_y = P.xs + X_Y;
      conv_channel(sb + OFF_U + w * U_CH, tb, lane, g_y + (size_t)d * 256 + lane);
      nb_arrive(NB_BDONE, 288);
      TS(37);
      mbar_wait(BAR(MB_OA));
      const int lam = w * 8 + g;
      const uint4* src = g_y + (size_t)(oct * 32 + c * 8) * 256 + i8 * 32 + lam;
      uint4 v[8];
#pragma unroll 1
      for (int it = 0; it < SPIN_MAX; it++) {
        uint32_t m = 0xffffffffu;
#pragma unroll
        for (int i = 0; i < 8; i++) v[i] = ld_x(src + i * 256);
#pragma unroll
        for (int i = 0; i < 8; i++) m = min(m, v[i].x);
        if (__all_sync(0xffffffffu, m != 0)) break;
      }
      __nv_bfloat16* dst = P.out + (size_t)(i8 * 256 + (lam >> 2) * 16 + (lam & 3) * 2) * 1024 + 512 + oct * 32 + c * 8;
#pragma unroll
      for (int i = 0; i < 8; i++) *(uint4*)(dst + (size_t)((i >> 2) * 128 + ((i >> 1) & 1) * 8 + (i & 1)) * 1024) = tr_row(v, i);
      TS(38);
      GT(63);
      if (w == 0) TSDUMP(32);
      return;
    }
    if (wg == 1) {
      mbar_wait(BAR(MB_URAW));
      TS(48);
      uint4* dst = P.xs + X_UT + (i8 * 64 + g) * (U_CH / 16) + (w & 1) * (U_ODD / 16) + U_PAD / 16 + oct * 8 + (w >> 1) * 4 + c;
      const int ln = ((lane >> 1) & 3) + 4 * (lane & 1);
      uint32_t r[8][4];
#pragma unroll
      for (int i = 0; i < 8; i++) ldsm4t(r[i], sb + OFF_STG0 + w * 4096 + ((lane >> 3) * 8 + ln) * 128 + ((i ^ ln) << 4));
#pragma unroll
      for (int i = 0; i < 8; i++) dst[i * (U_CH / 2)] = make_uint4(r[i][0], r[i][1], r[i][2], r[i][3]);
      nb_arrive(NB_INIT, 160);
      if (lane == 0) mbar_arrive(BAR(MB_AUX));
      mbar_wait(BAR(MB_EMPTY + 4));
      mbar_spin(BAR(MB_EMPTY + 6));
    }
    TS(wg * 16 + 1);
  }

  float acc[2][48];
  {
    uint32_t fb = BAR(MB_FULL) + 64 * wg;
    uint32_t da = (uint32_t)mkdesc(sb + OFF_X, 16, 0, 0) + (wg ? 1024 : 3072), db = (uint32_t)mkdesc(sb + OFF_W, 4096, 0, 0);
    constexpr uint64_t ha = mkdesc(0, 0, 1024, 1), hb = mkdesc(0, 0, 512, 2);
    mbar_spin(fb);
    TS(wg * 16 + 2);
#pragma unroll 1
    for (int kb = 0; kb < 8; kb++) {
      WG_FENCE();
#pragma unroll
      for (int k = 0; k < 4; k++) {
        wgmma_ss_n96(acc[0], ha | (da + 2 * k), hb | (db + 64 * k), k ? 1 : kb);
        wgmma_ss_n96(acc[1], ha | (da + 2 * k + 512), hb | (db + 64 * k), k ? 1 : kb);
      }
      WG_COMMIT();
      if (kb < 7) mbar_spin(fb + 8);
      WG_WAIT(1);
      if (kb > 0) e_arrive(fb + 8 * (MB_EMPTY - MB_FULL - 1));
      fb += 8; db += 768;
      da = da == (uint32_t)mkdesc(sb + OFF_X + 65536, 16, 0, 0) ? da - 4096 : da + 1024;
    }
    if (wg == 0) nb_sync(NB_KREAD, 160);
    WG_WAIT(0);
    e_arrive(fb + 8 * (MB_EMPTY - MB_FULL - 1));
    mbar_spin(fb + 8 * (MB_EMPTY - MB_FULL - 1));
  }
  TS(wg * 16 + 3);
  asm volatile("setmaxnreg.inc.sync.aligned.u32 160;");

  constexpr uint32_t stg0 = sb + OFF_STG0, stg1 = sb + OFF_X + 32768;
  uint4* const g_part = P.xs + X_PART;
  uint4* const g_o = P.xs + X_O;
  constexpr uint32_t kvs = stg0;
  auto pack8 = [](const float* a) { return make_uint4(pack_bf(a[0], a[1]), pack_bf(a[2], a[3]), pack_bf(a[4], a[5]), pack_bf(a[6], a[7])); };
  auto feat = [&](const uint4 (&af)[4], float (&p)[4][8]) {
    WG_FENCE();
#pragma unroll
    for (int u = 0; u < 4; u++) wgmma_rs_n16(p[u], af[u], qdesc(sb + OFF_PHI + (u & 1) * 512), 0);
    WG_COMMIT();
  };
  auto packp = [](const float (&p)[4][8], uint32_t (&pw)[16]) {
#pragma unroll
    for (int i = 0; i < 16; i++) pw[i] = pack_bf(p[i >> 2][(i & 1) + 2 * (i & 2)], p[i >> 2][(i & 1) + 2 * (i & 2) + 2]);
  };
  auto contract = [&](float (&kc)[20], uint32_t stg, int acc_in) {
    WG_FENCE();
#pragma unroll
    for (int s = 0; s < 8; s++) wgmma_ss_n40(kc, qdesc(stg + s * SLAB), qdesc(stg + s * SLAB + 2048), s ? 1 : acc_in);
    WG_COMMIT();
    WG_WAIT(0);
  };
  uint32_t eq[32];
  {
    uint4 af[4], aq[4], vp[4];
    float p[4][8];
#pragma unroll
    for (int u = 0; u < 4; u++) af[u] = pack8(acc[u >> 1] + 16 + 8 * (u & 1));
    feat(af, p);
#pragma unroll
    for (int u = 0; u < 4; u++) { aq[u] = pack8(acc[u >> 1] + 8 * (u & 1)); vp[u] = pack8(acc[u >> 1] + 32 + 8 * (u & 1)); }
    WG_WAIT(0);
    uint32_t pw[16], ek[32];
    packp(p, pw);
#pragma unroll
    for (int u = 0; u < 4; u++) dual_exp(pw + 4 * u, ek + 8 * u);
    TS(wg * 16 + 12);
    mbar_wait(BAR(MB_AUX));
    float rs[8][4];
    WG_FENCE();
#pragma unroll
    for (int i = 0; i < 8; i++) wgmma_rs_n8(rs[i], make_uint4(ek[4 * i], ek[4 * i + 1], ek[4 * i + 2], ek[4 * i + 3]), qdesc(sb + OFF_ONE), 0);
    WG_COMMIT();
    feat(aq, p);
    const uint32_t sl = (wg ? stg1 : stg0) + w * SLAB + lane * 16;
#pragma unroll
    for (int i = 0; i < 4; i++) stsm4(sl + (i >> 1) * 4 * SLAB + 2048 + (i & 1) * 512, vp[i].x, vp[i].y, vp[i].z, vp[i].w);
    sts128(sl + (lane >> 4) * (4 * SLAB - 256) + 3072, 0x3F803F80u, 0x3F803F80u, 0x3F803F80u, 0x3F803F80u);
    WG_WAIT(1);
#pragma unroll
    for (int i = 0; i < 8; i++) {
      normalise(ek + 4 * i, rs[i]);
      stsm4(sl + (i >> 2) * 4 * SLAB + (i & 3) * 512, ek[4 * i], ek[4 * i + 1], ek[4 * i + 2], ek[4 * i + 3]);
    }
    asm volatile("fence.proxy.async.shared::cta;" ::: "memory");
    TS(wg * 16 + 13);
    if (wg) {
      nb_arrive(NB_ST0, 256);
    } else {
      float kc[20];
      uint4* pp = g_part + (size_t)(hp * 8 + rt) * 144 + t;
      uint32_t* pz = (uint32_t*)(pp - t + 128) + w * 16 + c * 8 + g;
      asm volatile("" : "+l"(pp), "+l"(pz));
      nb_sync(NB_WG0, 128);
      contract(kc, stg0, 0);
      mbar_wait(BAR(MB_UFULL));
      TS(15);
      nb_sync(NB_ST0, 256);
      contract(kc, stg1, 1);
      TS(6);
      float kv[8];
#pragma unroll
      for (int i = 0; i < 8; i++) kv[i] = w & 2 ? kc[8 + i] : kc[i];
      st_x(pp, nz(pack_bf(kv[0], kv[1])), pack_bf(kv[2], kv[3]), pack_bf(kv[4], kv[5]), pack_bf(kv[6], kv[7]));
      if (c < 2) st_x32(pz, nz(fu(c ? kc[18] : kc[16])));
      TS(5);
    }
    SPLIT();
    WG_WAIT(0);
    packp(p, pw);
#pragma unroll
    for (int u = 0; u < 4; u++) dual_exp(pw + 4 * u, eq + 8 * u);
    SPLIT();
  }
  TS(wg * 16 + 4);
  if (wg == 1) {
    mbar_wait(BAR(MB_UFULL));
    const uint4* ps = g_part + (size_t)hp * 8 * 144 + t;
    const uint32_t* zs = (const uint32_t*)(g_part + (size_t)(hp * 8 + (lane >> 4) * 4) * 144 + 128) + w * 16 + (lane & 15);
    uint4 v[8];
    uint32_t zv[4];
#pragma unroll 1
    for (int it = 0; it < SPIN_MAX; it++) {
#pragma unroll
      for (int i = 0; i < 8; i++) v[i] = ld_x(ps + i * 144);
#pragma unroll
      for (int i = 0; i < 4; i++) zv[i] = ld_x32(zs + i * 576);
      uint32_t m = min(min(zv[0], zv[1]), min(zv[2], zv[3]));
#pragma unroll
      for (int i = 0; i < 8; i++) m = min(m, v[i].x);
      if (__all_sync(0xffffffffu, m != 0)) break;
    }
    float s[8];
    WG_FENCE();
#pragma unroll
    for (int r = 0; r < 8; r++) wgmma_rs_n16(s, v[r], qdesc(sb + OFF_EYE), r);
    WG_COMMIT();
    float zsum = (uf(zv[0]) + uf(zv[1])) + (uf(zv[2]) + uf(zv[3]));
    zsum += __shfl_xor_sync(0xffffffffu, zsum, 16);
    const uint32_t z1 = pack_bf(zsum, 1.f);
    if (lane < 16) sts128(kvs + w * 768 + 512 + lane * 16, z1, z1, z1, z1);
    WG_WAIT(0);
    stsm4(kvs + w * 768 + lane * 16, pack_bf(s[0], s[1]), pack_bf(s[2], s[3]), pack_bf(s[4], s[5]), pack_bf(s[6], s[7]));
    asm volatile("fence.proxy.async.shared::cta;" ::: "memory");
    TS(22);
  }
  nb_sync(NB_KV, 256);
  {
    float n[8][12];
    WG_FENCE();
#pragma unroll
    for (int i = 0; i < 8; i++) wgmma_rs_n24(n[i], make_uint4(eq[4 * i], eq[4 * i + 1], eq[4 * i + 2], eq[4 * i + 3]), qdesc(kvs + (i & 3) * 768), 0);
    WG_COMMIT();
    uint32_t* od = (uint32_t*)(g_o + (size_t)((rt * 4 + wg * 2) * 32 + hp * 2) * 128) + w * 64 + lane;
    WG_WAIT(0);
#pragma unroll
    for (int u = 0; u < 4; u++) {
      float(&np)[12] = n[2 * u];
      const float(&nm)[12] = n[2 * u + 1];
      const float q0 = np[9] * rcp(nm[9]), q1 = np[11] * rcp(nm[11]);
      const float r0 = rcp(fmaf(nm[8], q0, fmaf(np[9], 1e-6f, np[8]))), r1 = rcp(fmaf(nm[10], q1, fmaf(np[11], 1e-6f, np[10])));
#pragma unroll
      for (int i = 0; i < 8; i++) np[i] = fmaf(nm[i], (i & 2) ? q1 : q0, np[i]);
      uint32_t* o = od + (u >> 1) * 16384 + (u & 1) * 512;
      o[0] = pack_bf(np[0] * r0, np[1] * r0);
      o[32] = pack_bf(np[2] * r1, np[3] * r1);
      o[256] = pack_bf(np[4] * r0, np[5] * r0);
      o[288] = pack_bf(np[6] * r1, np[7] * r1);
      if (u == 1) SPLIT();
    }
  }
  TS(wg * 16 + 7);
  nb_arrive(NB_ODONE, 320);
  if (wg) { if (w == 0) TSDUMP(16); return; }
  mbar_wait(BAR(MB_WO));
  mbar_wait(BAR(MB_OA));
  TS(8);
  nb_sync(NB_BDONE, 288);
  TS(9);
  float oc[64];
  {
    constexpr uint64_t ha = mkdesc(0, 0, 128, 0), hb = mkdesc(0, 0, 1024, 1);
    constexpr uint32_t da0 = (uint32_t)mkdesc(stg1, 1024, 0, 0), db0 = (uint32_t)mkdesc(sb + OFF_W, 8192, 0, 0);
#pragma unroll 1
    for (int j = 0; j < 8; j++) {
      const int kb = (j + 7) & 7;
      if ((j & 3) == 1) mbar_spin(j == 1 ? BAR(MB_OC) : BAR(MB_OB));
      WG_FENCE();
#pragma unroll
      for (int k = 0; k < 4; k++) wgmma_ss_n128(oc, ha | (da0 + 512 * kb + 128 * k), hb | (db0 + 1024 * kb + 128 * k), k ? 1 : j);
      WG_COMMIT();
    }
    WG_WAIT(0);
  }
  TS(10);
  nb_sync(NB_WG0, 128);
  const uint32_t ot = sb + OFF_W + w * 4096;
#pragma unroll
  for (int i = 0; i < 16; i += 2)
    stsm4(ot + (i >> 3) * 2048 + (lane & 15) * 128 + (((i + (lane >> 4)) ^ lane) & 7) * 16, pack_bf(oc[4 * i], oc[4 * i + 1]),
          pack_bf(oc[4 * i + 2], oc[4 * i + 3]), pack_bf(oc[4 * i + 4], oc[4 * i + 5]), pack_bf(oc[4 * i + 6], oc[4 * i + 7]));
  asm volatile("fence.proxy.async.shared::cta;" ::: "memory");
  __syncwarp();
  e_store3d(&mout, ot, (rt * 4 + (hp >> 2)) * 64 + w * 16, (hp & 3) * 2);
  TS(wg * 16 + 11);
  GT(61 + wg);
  if (w == 0) TSDUMP(0);
  if (w == 1) TSDUMP(48);
}

typedef CUresult (*EncodeFn)(CUtensorMap*, CUtensorMapDataType, cuuint32_t, void*, const cuuint64_t*, const cuuint64_t*,
                             const cuuint32_t*, const cuuint32_t*, CUtensorMapInterleave, CUtensorMapSwizzle,
                             CUtensorMapL2promotion, CUtensorMapFloatOOBfill);

}

extern "C" void kernel_launch(void* const* d_in, const int* in_sizes, int n_in, void* d_out, int out_size) {
  (void)in_sizes; (void)n_in; (void)out_size;
  void* fn = nullptr;
  cudaDriverEntryPointQueryResult qr;
  cudaGetDriverEntryPoint("cuTensorMapEncodeTiled", &fn, cudaEnableDefault, &qr);
  EncodeFn enc = (EncodeFn)fn;
  CUtensorMap mx, mw, mo, mu, mout, mw4;
  const cuuint32_t es[5] = {1, 1, 1, 1, 1};
  {
    cuuint64_t dims[2] = {512, 2048}, st[1] = {1024};
    cuuint32_t box[2] = {64, 128};
    enc(&mx, CU_TENSOR_MAP_DATA_TYPE_BFLOAT16, 2, d_in[0], dims, st, box, es, CU_TENSOR_MAP_INTERLEAVE_NONE,
        CU_TENSOR_MAP_SWIZZLE_128B, CU_TENSOR_MAP_L2_PROMOTION_L2_128B, CU_TENSOR_MAP_FLOAT_OOB_FILL_NONE);
  }
  {
    cuuint64_t dims[3] = {512, 512, 3}, st[2] = {3072, 1024};
    cuuint32_t box[3] = {32, 64, 3};
    enc(&mw, CU_TENSOR_MAP_DATA_TYPE_BFLOAT16, 3, d_in[1], dims, st, box, es, CU_TENSOR_MAP_INTERLEAVE_NONE,
        CU_TENSOR_MAP_SWIZZLE_64B, CU_TENSOR_MAP_L2_PROMOTION_L2_128B, CU_TENSOR_MAP_FLOAT_OOB_FILL_NONE);
  }
  {
    cuuint64_t dims[3] = {64, 512, 8}, st[2] = {1024, 128};
    cuuint32_t box[3] = {64, 64, 2};
    enc(&mo, CU_TENSOR_MAP_DATA_TYPE_BFLOAT16, 3, d_in[3], dims, st, box, es, CU_TENSOR_MAP_INTERLEAVE_NONE,
        CU_TENSOR_MAP_SWIZZLE_128B, CU_TENSOR_MAP_L2_PROMOTION_L2_128B, CU_TENSOR_MAP_FLOAT_OOB_FILL_NONE);
  }
  {
    cuuint64_t dims[4] = {512, 4, 16, 32}, st[3] = {16384, 1024, 65536};
    cuuint32_t box[4] = {64, 4, 16, 2};
    enc(&mu, CU_TENSOR_MAP_DATA_TYPE_BFLOAT16, 4, d_in[4], dims, st, box, es, CU_TENSOR_MAP_INTERLEAVE_NONE,
        CU_TENSOR_MAP_SWIZZLE_128B, CU_TENSOR_MAP_L2_PROMOTION_L2_128B, CU_TENSOR_MAP_FLOAT_OOB_FILL_NONE);
  }
  {
    cuuint64_t dims[3] = {64, 2048, 16}, st[2] = {2048, 128};
    cuuint32_t box[3] = {64, 16, 2};
    enc(&mout, CU_TENSOR_MAP_DATA_TYPE_BFLOAT16, 3, d_out, dims, st, box, es, CU_TENSOR_MAP_INTERLEAVE_NONE,
        CU_TENSOR_MAP_SWIZZLE_128B, CU_TENSOR_MAP_L2_PROMOTION_NONE, CU_TENSOR_MAP_FLOAT_OOB_FILL_NONE);
  }
  {
    cuuint64_t dims[4] = {512, 64, 3, 8}, st[3] = {3072, 1024, 64 * 3072};
    cuuint32_t box[4] = {32, 64, 3, 4};
    enc(&mw4, CU_TENSOR_MAP_DATA_TYPE_BFLOAT16, 4, d_in[1], dims, st, box, es, CU_TENSOR_MAP_INTERLEAVE_NONE,
        CU_TENSOR_MAP_SWIZZLE_64B, CU_TENSOR_MAP_L2_PROMOTION_L2_128B, CU_TENSOR_MAP_FLOAT_OOB_FILL_NONE);
  }
  Params P;
  P.x = (const __nv_bfloat16*)d_in[0];
  P.wphi = (const __nv_bfloat16*)d_in[2];
  P.wo = (const __nv_bfloat16*)d_in[3];
  P.logA = (const __nv_bfloat16*)d_in[5];
  P.Aim = (const __nv_bfloat16*)d_in[6];
  P.Cre = (const __nv_bfloat16*)d_in[7];
  P.Cim = (const __nv_bfloat16*)d_in[8];
  P.logdt = (const __nv_bfloat16*)d_in[9];
  P.Dskip = (const __nv_bfloat16*)d_in[10];
  P.out = (__nv_bfloat16*)d_out;
  cudaGetSymbolAddress((void**)&P.xs, g_x);
  P.ts = nullptr;
  cudaFuncSetAttribute(fused_kernel, cudaFuncAttributeMaxDynamicSharedMemorySize, SMEM_BYTES);
  fused_kernel<<<NCTA, NTHREADS, SMEM_BYTES>>>(P, mx, mw, mo, mu, mout, mw4);
}
```

```cpp
#include <cuda_runtime.h>
#include <cuda_bf16.h>
#include <cuda_fp16.h>
#include <cuda.h>
#include <stdint.h>

#define DBG_TS 0

namespace {

constexpr int NTHREADS = 512;
constexpr int NCTA = 128;
constexpr int OFF_W = 0;
constexpr int OFF_X = 98304;
constexpr int OFF_U = OFF_X + 65536;
constexpr int U_CH = 4416, U_ODD = 2240, U_PAD = 128;
constexpr int OFF_STG0 = OFF_U + 18432;
constexpr int SLAB = 3328;
constexpr int OFF_T = OFF_STG0 + 8 * SLAB;
constexpr int T_CH = 5216;
constexpr int T_D = 0;
constexpr int T_5 = 2144;
constexpr int T_3 = T_5 + 384;
constexpr int T_7 = T_5 + 1024;
constexpr int T_9 = T_7 + 320;
constexpr int T_KC = T_9 + 320;
constexpr int T_ST = T_5 - 1024;
constexpr int OFF_PHI = OFF_T + 4 * T_CH;
constexpr int OFF_EYE = OFF_PHI + 1024, OFF_ONE = OFF_EYE + 512;
constexpr int OFF_BAR = OFF_ONE + 256;
constexpr int SMEM_BYTES = OFF_BAR + 512 + 256 * DBG_TS;
constexpr uint32_t SB = 1024;
static_assert(T_KC + 2 * 656 <= T_CH, "table size");
static_assert(SMEM_BYTES <= 232448, "smem");
constexpr int MB_URAW = 0, MB_FULL = 1  , MB_WO = 17, MB_UFULL = 18, MB_OA = 19, MB_OB = 20, MB_OC = 21,
              MB_EMPTY = 22  , MB_AUX = 38;
__host__ __device__ constexpr uint32_t BAR(int i) { return SB + OFF_BAR + 8 * i; }
constexpr int NB_WG0 = 1, NB_ODONE = 2, NB_ST0 = 3  , NB_KV = 5, NB_YZ = 6, NB_INIT = 7, NB_PREP = 8, NB_PROD = 9, NB_KREAD = 10, NB_BDONE = 11, NB_ZERO = 12;
#define U_AT 2
#define ZERO_STEP 15
constexpr int SPIN_MAX = 1 << 16;

constexpr int X_CNT = 0;
constexpr int X_PART = 128;
constexpr int X_O = X_PART + 16 * 8 * 144;
constexpr int X_Y = X_O + 32 * 32 * 128;
constexpr int X_UT = X_Y + 512 * 8 * 32;
constexpr int X_SIZE = X_UT + 512 * (U_CH / 16);
__device__ __align__(128) uint4 g_x[X_SIZE];
extern __shared__ uint8_t smem_raw[];
#define TS(i) do {} while (0)
#define TS1(i) do {} while (0)
#define GT(i) do {} while (0)
#define TSDUMP(base) do {} while (0)

__device__ __forceinline__ uint32_t smem_u32(const void* p) { return (uint32_t)__cvta_generic_to_shared(p); }
__device__ __forceinline__ void mbar_arrive(uint32_t b) {
  asm volatile("mbarrier.arrive.shared::cta.b64 _, [%0];" ::"r"(b) : "memory");
}
__device__ __forceinline__ void mbar_wait(uint32_t b) {
  uint32_t done = 0;
#pragma unroll 1
  for (int i = 0; i < SPIN_MAX && !done; i++) {
    asm volatile("{\n.reg .pred p;\nmbarrier.try_wait.parity.shared::cta.b64 p, [%1], 0, 4000;\nselp.u32 %0, 1, 0, p;\n}\n"
                 : "=r"(done) : "r"(b) : "memory");
  }
}
__device__ __forceinline__ void mbar_spin(uint32_t b) {
  uint32_t done = 0;
#pragma unroll 1
  for (int i = 0; i < (SPIN_MAX << 4) && !done; i++) {
    asm volatile("{\n.reg .pred p;\nmbarrier.try_wait.parity.shared::cta.b64 p, [%1], 0;\nselp.u32 %0, 1, 0, p;\n}\n"
                 : "=r"(done) : "r"(b) : "memory");
  }
}
__device__ __forceinline__ void mbar_init(uint32_t b, int n) {
  asm volatile("mbarrier.init.shared::cta.b64 [%0], %1;" ::"r"(b), "r"(n) : "memory");
}
__device__ __forceinline__ void mbar_expect(uint32_t b, int bytes) {
  asm volatile("mbarrier.arrive.expect_tx.shared::cta.b64 _, [%0], %1;" ::"r"(b), "r"(bytes) : "memory");
}
__device__ __forceinline__ void nb_sync(int id, int n) { asm volatile("bar.sync %0, %1;" ::"r"(id), "r"(n) : "memory"); }
__device__ __forceinline__ void nb_arrive(int id, int n) { asm volatile("bar.arrive %0, %1;" ::"r"(id), "r"(n) : "memory"); }
#define ELECT "{\n.reg .pred p;\nelect.sync _|p, 0xffffffff;\n@p "
__device__ __forceinline__ void e_arrive(uint32_t b) {
  asm volatile(ELECT "mbarrier.arrive.shared::cta.b64 _, [%0];\n}\n" ::"r"(b) : "memory");
}
__device__ __forceinline__ void e_expect(uint32_t b, int bytes) {
  asm volatile(ELECT "mbarrier.arrive.expect_tx.shared::cta.b64 _, [%0], %1;\n}\n" ::"r"(b), "r"(bytes) : "memory");
}
__device__ __forceinline__ void e_tma2d(uint32_t dst, const CUtensorMap* m, uint32_t bar, int c0, int c1) {
  asm volatile(ELECT "cp.async.bulk.tensor.2d.shared::cluster.global.mbarrier::complete_tx::bytes [%0], [%1, {%3,%4}], [%2];\n}\n"
               ::"r"(dst), "l"(m), "r"(bar), "r"(c0), "r"(c1) : "memory");
}
__device__ __forceinline__ void e_tma3d(uint32_t dst, const CUtensorMap* m, uint32_t bar, int c0, int c1, int c2) {
  asm volatile(ELECT "cp.async.bulk.tensor.3d.shared::cluster.global.mbarrier::complete_tx::bytes [%0], [%1, {%3,%4,%5}], [%2];\n}\n"
               ::"r"(dst), "l"(m), "r"(bar), "r"(c0), "r"(c1), "r"(c2) : "memory");
}
__device__ __forceinline__ void e_tma4d(uint32_t dst, const CUtensorMap* m, uint32_t bar, int c0, int c3) {
  asm volatile(ELECT "cp.async.bulk.tensor.4d.shared::cluster.global.mbarrier::complete_tx::bytes [%0], [%1, {%3,%5,%5,%4}], [%2];\n}\n"
               ::"r"(dst), "l"(m), "r"(bar), "r"(c0), "r"(c3), "r"(0) : "memory");
}
__device__ __forceinline__ void e_bulk(uint32_t dst, const void* src, int bytes, uint32_t bar) {
  asm volatile(ELECT "cp.async.bulk.shared::cluster.global.mbarrier::complete_tx::bytes [%0], [%1], %2, [%3];\n}\n"
               ::"r"(dst), "l"(src), "r"(bytes), "r"(bar) : "memory");
}
__device__ __forceinline__ void e_prefetch(const void* p, int bytes) {
  asm volatile(ELECT "cp.async.bulk.prefetch.L2.global [%0], %1;\n}\n" ::"l"(p), "r"(bytes) : "memory");
}
__device__ __forceinline__ void e_store2d(const CUtensorMap* m, uint32_t src, int c0, int c1) {
  asm volatile(ELECT "cp.async.bulk.tensor.2d.global.shared::cta.bulk_group [%0, {%2,%3}], [%1];\n}\n"
               ::"l"(m), "r"(src), "r"(c0), "r"(c1) : "memory");
}
__host__ __device__ constexpr uint64_t mkdesc(uint32_t addr, uint32_t lbo, uint32_t sbo, int swz) {
  return (uint64_t)((addr & 0x3FFFF) >> 4) | ((uint64_t)(lbo >> 4) << 16) | ((uint64_t)(sbo >> 4) << 32) |
         ((uint64_t)swz << 62);
}
#define SPLIT() asm volatile("{\n.reg .pred p;\nsetp.eq.u32 p, %0, %1;\n@p exit;\n}\n" ::"r"(blockIdx.y), "n"(__LINE__) : "memory")
#define WG_FENCE() asm volatile("wgmma.fence.sync.aligned;" ::: "memory")
#define WG_COMMIT() asm volatile("wgmma.commit_group.sync.aligned;" ::: "memory")
#define WG_WAIT(n) asm volatile("wgmma.wait_group.sync.aligned " #n ";" ::: "memory")

__device__ __forceinline__ void mma(float& d0, float& d1, float& d2, float& d3, uint32_t a0, uint32_t a1, uint32_t a2,
                                    uint32_t a3, uint32_t b0, uint32_t b1) {
  asm volatile("mma.sync.aligned.m16n8k16.row.col.f32.bf16.bf16.f32 {%0,%1,%2,%3},{%4,%5,%6,%7},{%8,%9},{%0,%1,%2,%3};"
               : "+f"(d0), "+f"(d1), "+f"(d2), "+f"(d3)
               : "r"(a0), "r"(a1), "r"(a2), "r"(a3), "r"(b0), "r"(b1));
}
__device__ __forceinline__ void mmac(float (&d)[4], uint32_t a0, uint32_t a1, uint32_t a2, uint32_t a3, uint32_t b0,
                                     uint32_t b1, const float (&c)[4]) {
  asm volatile("mma.sync.aligned.m16n8k16.row.col.f32.bf16.bf16.f32 {%0,%1,%2,%3},{%4,%5,%6,%7},{%8,%9},{%10,%11,%12,%13};"
               : "=f"(d[0]), "=f"(d[1]), "=f"(d[2]), "=f"(d[3])
               : "r"(a0), "r"(a1), "r"(a2), "r"(a3), "r"(b0), "r"(b1), "f"(c[0]), "f"(c[1]), "f"(c[2]), "f"(c[3]));
}
__device__ __forceinline__ void mma_p(int p, float (&d)[4], uint32_t a0, uint32_t a1, uint32_t a2, uint32_t a3, uint32_t b0, uint32_t b1) {
  asm volatile("{\n.reg .pred q;\nsetp.ne.b32 q, %10, 0;\n"
               "@q mma.sync.aligned.m16n8k16.row.col.f32.bf16.bf16.f32 {%0,%1,%2,%3},{%4,%5,%6,%7},{%8,%9},{%0,%1,%2,%3};\n}\n"
               : "+f"(d[0]), "+f"(d[1]), "+f"(d[2]), "+f"(d[3])
               : "r"(a0), "r"(a1), "r"(a2), "r"(a3), "r"(b0), "r"(b1), "r"(p));
}
__device__ __forceinline__ void mmac_p(int p, float (&d)[4], uint32_t a0, uint32_t a1, uint32_t a2, uint32_t a3, uint32_t b0,
                                       uint32_t b1, const float (&c)[4]) {
  asm volatile("{\n.reg .pred q;\nsetp.ne.b32 q, %14, 0;\n"
               "@q mma.sync.aligned.m16n8k16.row.col.f32.bf16.bf16.f32 {%0,%1,%2,%3},{%4,%5,%6,%7},{%8,%9},{%10,%11,%12,%13};\n}\n"
               : "+f"(d[0]), "+f"(d[1]), "+f"(d[2]), "+f"(d[3])
               : "r"(a0), "r"(a1), "r"(a2), "r"(a3), "r"(b0), "r"(b1), "f"(c[0]), "f"(c[1]), "f"(c[2]), "f"(c[3]), "r"(p));
}
__device__ __forceinline__ void mma_h(float (&d)[4], const uint32_t (&a)[4], uint32_t b0, uint32_t b1) {
  asm volatile("mma.sync.aligned.m16n8k16.row.col.f32.f16.f16.f32 {%0,%1,%2,%3},{%4,%5,%6,%7},{%8,%9},{%0,%1,%2,%3};"
               : "+f"(d[0]), "+f"(d[1]), "+f"(d[2]), "+f"(d[3]) : "r"(a[0]), "r"(a[1]), "r"(a[2]), "r"(a[3]), "r"(b0), "r"(b1));
}
__device__ __forceinline__ void mma0(float& d0, float& d1, float& d2, float& d3, uint32_t a0, uint32_t a1, uint32_t a2,
                                     uint32_t a3, uint32_t b0, uint32_t b1) {
  asm volatile("mma.sync.aligned.m16n8k16.row.col.f32.bf16.bf16.f32 {%0,%1,%2,%3},{%4,%5,%6,%7},{%8,%9},{%10,%10,%10,%10};"
               : "=f"(d0), "=f"(d1), "=f"(d2), "=f"(d3)
               : "r"(a0), "r"(a1), "r"(a2), "r"(a3), "r"(b0), "r"(b1), "f"(0.f));
}
__device__ __forceinline__ uint32_t pack_bf(float lo, float hi) {
  uint32_t r;
  asm("cvt.rn.bf16x2.f32 %0, %1, %2;" : "=r"(r) : "f"(hi), "f"(lo));
  return r;
}
__device__ __forceinline__ float bf_lo(uint32_t w) { return __uint_as_float(w << 16); }
__device__ __forceinline__ float bf_hi(uint32_t w) { return __uint_as_float(w & 0xffff0000u); }
__device__ __forceinline__ float bf_round(float x) { return __bfloat162float(__float2bfloat16_rn(x)); }
__device__ __forceinline__ uint32_t bmax2(uint32_t a, uint32_t b) {
  uint32_t r; asm("max.bf16x2 %0, %1, %2;" : "=r"(r) : "r"(a), "r"(b)); return r;
}
__device__ __forceinline__ uint32_t bmin2(uint32_t a, uint32_t b) {
  uint32_t r; asm("min.bf16x2 %0, %1, %2;" : "=r"(r) : "r"(a), "r"(b)); return r;
}
__device__ __forceinline__ float ex2(float x) { float r; asm("ex2.approx.ftz.f32 %0, %1;" : "=f"(r) : "f"(x)); return r; }
__device__ __forceinline__ float rcp(float x) { float r; asm("rcp.approx.ftz.f32 %0, %1;" : "=f"(r) : "f"(x)); return r; }
__device__ __forceinline__ void ldsm4(uint32_t (&r)[4], uint32_t a) {
  asm volatile("ldmatrix.sync.aligned.m8n8.x4.shared.b16 {%0,%1,%2,%3}, [%4];"
               : "=r"(r[0]), "=r"(r[1]), "=r"(r[2]), "=r"(r[3]) : "r"(a) : "memory");
}
__device__ __forceinline__ void ldsm4t(uint32_t (&r)[4], uint32_t a) {
  asm volatile("ldmatrix.sync.aligned.m8n8.x4.trans.shared.b16 {%0,%1,%2,%3}, [%4];"
               : "=r"(r[0]), "=r"(r[1]), "=r"(r[2]), "=r"(r[3]) : "r"(a) : "memory");
}
__device__ __forceinline__ void stsm4(uint32_t a, uint32_t r0, uint32_t r1, uint32_t r2, uint32_t r3) {
  asm volatile("stmatrix.sync.aligned.m8n8.x4.shared.b16 [%0], {%1,%2,%3,%4};"
               ::"r"(a), "r"(r0), "r"(r1), "r"(r2), "r"(r3) : "memory");
}
__device__ __forceinline__ uint32_t lds32(uint32_t a) {
  uint32_t r; asm volatile("ld.shared.u32 %0, [%1];" : "=r"(r) : "r"(a) : "memory"); return r;
}
__device__ __forceinline__ uint32_t lds16(uint32_t a) {
  uint32_t r; asm volatile("{\n.reg .u16 h;\nld.shared.u16 h, [%1];\ncvt.u32.u16 %0, h;\n}\n" : "=r"(r) : "r"(a) : "memory"); return r;
}
__device__ __forceinline__ uint2 lds64(uint32_t a) {
  uint2 r; asm volatile("ld.shared.v2.u32 {%0,%1}, [%2];" : "=r"(r.x), "=r"(r.y) : "r"(a) : "memory"); return r;
}
__device__ __forceinline__ uint4 lds128(uint32_t a) {
  uint4 r;
  asm volatile("ld.shared.v4.u32 {%0,%1,%2,%3}, [%4];" : "=r"(r.x), "=r"(r.y), "=r"(r.z), "=r"(r.w) : "r"(a) : "memory");
  return r;
}
__device__ __forceinline__ void sts32(uint32_t a, uint32_t v) { asm volatile("st.shared.u32 [%0], %1;" ::"r"(a), "r"(v) : "memory"); }
__device__ __forceinline__ void sts16(uint32_t a, uint32_t v) {
  asm volatile("{\n.reg .u16 h;\ncvt.u16.u32 h, %1;\nst.shared.u16 [%0], h;\n}\n" ::"r"(a), "r"(v) : "memory");
}
__device__ __forceinline__ void sts64(uint32_t a, uint32_t x, uint32_t y) {
  asm volatile("st.shared.v2.u32 [%0], {%1,%2};" ::"r"(a), "r"(x), "r"(y) : "memory");
}
__device__ __forceinline__ void sts128(uint32_t a, uint32_t x, uint32_t y, uint32_t z, uint32_t w) {
  asm volatile("st.shared.v4.u32 [%0], {%1,%2,%3,%4};" ::"r"(a), "r"(x), "r"(y), "r"(z), "r"(w) : "memory");
}
__device__ __forceinline__ uint4 ld_x(const uint4* p) {
  uint4 r;
  asm volatile("{\n.reg .b128 t;\nld.relaxed.gpu.global.b128 t, [%4];\nmov.b128 {%0,%1,%2,%3}, t;\n}\n"
               : "=r"(r.x), "=r"(r.y), "=r"(r.z), "=r"(r.w) : "l"(p) : "memory");
  return r;
}
__device__ __forceinline__ uint32_t ld_x32(const uint32_t* p) {
  uint32_t r; asm volatile("ld.relaxed.gpu.global.u32 %0, [%1];" : "=r"(r) : "l"(p) : "memory"); return r;
}
__device__ __forceinline__ void st_x(uint4* p, uint32_t x, uint32_t y, uint32_t z, uint32_t w) {
  asm volatile("{\n.reg .b128 t;\nmov.b128 t, {%1,%2,%3,%4};\nst.relaxed.gpu.global.b128 [%0], t;\n}\n"
               ::"l"(p), "r"(x), "r"(y), "r"(z), "r"(w) : "memory");
}
__device__ __forceinline__ void st_x_p(int p, uint4* a, uint32_t x, uint32_t y, uint32_t z, uint32_t w) {
  asm volatile("{\n.reg .b128 t;\n.reg .pred q;\nsetp.ne.b32 q, %5, 0;\nmov.b128 t, {%1,%2,%3,%4};\n@q st.relaxed.gpu.global.b128 [%0], t;\n}\n"
               ::"l"(a), "r"(x), "r"(y), "r"(z), "r"(w), "r"(p) : "memory");
}
__device__ __forceinline__ void sts64_p(int p, uint32_t a, uint32_t x, uint32_t y) {
  asm volatile("{\n.reg .pred q;\nsetp.ne.b32 q, %3, 0;\n@q st.shared.v2.u32 [%0], {%1,%2};\n}\n" ::"r"(a), "r"(x), "r"(y), "r"(p) : "memory");
}
__device__ __forceinline__ void st_x32(uint32_t* p, uint32_t x) {
  asm volatile("st.relaxed.gpu.global.u32 [%0], %1;" ::"l"(p), "r"(x) : "memory");
}
__device__ __forceinline__ uint32_t nz(uint32_t w) { return max(w, 1u); }
__device__ __forceinline__ uint32_t fu(float x) { return __float_as_uint(x); }
__device__ __forceinline__ float uf(uint32_t x) { return __uint_as_float(x); }

__device__ __forceinline__ void wgmma_ss_n96(float (&d)[48], uint64_t da, uint64_t db, int sc) {
  asm volatile("{\n.reg .pred p;\nsetp.ne.b32 p, %50, 0;\n"
      "wgmma.mma_async.sync.aligned.m64n96k16.f32.bf16.bf16 "
      "{%0,%1,%2,%3,%4,%5,%6,%7,%8,%9,%10,%11,%12,%13,%14,%15,%16,%17,%18,%19,%20,%21,%22,%23,%24,%25,%26,%27,%28,%29,%30,%31,%32,%33,%34,%35,%36,%37,%38,%39,%40,%41,%42,%43,%44,%45,%46,%47}, "
      "%48, %49, p, 1, 1, 0, 1;\n}\n"
      : "+f"(d[0]), "+f"(d[1]), "+f"(d[2]), "+f"(d[3]), "+f"(d[4]), "+f"(d[5]), "+f"(d[6]), "+f"(d[7]),
        "+f"(d[8]), "+f"(d[9]), "+f"(d[10]), "+f"(d[11]), "+f"(d[12]), "+f"(d[13]), "+f"(d[14]), "+f"(d[15]),
        "+f"(d[16]), "+f"(d[17]), "+f"(d[18]), "+f"(d[19]), "+f"(d[20]), "+f"(d[21]), "+f"(d[22]), "+f"(d[23]),
        "+f"(d[24]), "+f"(d[25]), "+f"(d[26]), "+f"(d[27]), "+f"(d[28]), "+f"(d[29]), "+f"(d[30]), "+f"(d[31]),
        "+f"(d[32]), "+f"(d[33]), "+f"(d[34]), "+f"(d[35]), "+f"(d[36]), "+f"(d[37]), "+f"(d[38]), "+f"(d[39]),
        "+f"(d[40]), "+f"(d[41]), "+f"(d[42]), "+f"(d[43]), "+f"(d[44]), "+f"(d[45]), "+f"(d[46]), "+f"(d[47])
      : "l"(da), "l"(db), "r"(sc));
}

__device__ __forceinline__ void wgmma_ss_n128(float (&d)[64], uint64_t da, uint64_t db, int sc) {
  asm volatile("{\n.reg .pred p;\nsetp.ne.b32 p, %66, 0;\n"
      "wgmma.mma_async.sync.aligned.m64n128k16.f32.bf16.bf16 "
      "{%0,%1,%2,%3,%4,%5,%6,%7,%8,%9,%10,%11,%12,%13,%14,%15,%16,%17,%18,%19,%20,%21,%22,%23,%24,%25,%26,%27,%28,%29,%30,%31,%32,%33,%34,%35,%36,%37,%38,%39,%40,%41,%42,%43,%44,%45,%46,%47,%48,%49,%50,%51,%52,%53,%54,%55,%56,%57,%58,%59,%60,%61,%62,%63}, "
      "%64, %65, p, 1, 1, 0, 1;\n}\n"
      : "+f"(d[0]), "+f"(d[1]), "+f"(d[2]), "+f"(d[3]), "+f"(d[4]), "+f"(d[5]), "+f"(d[6]), "+f"(d[7]),
        "+f"(d[8]), "+f"(d[9]), "+f"(d[10]), "+f"(d[11]), "+f"(d[12]), "+f"(d[13]), "+f"(d[14]), "+f"(d[15]),
        "+f"(d[16]), "+f"(d[17]), "+f"(d[18]), "+f"(d[19]), "+f"(d[20]), "+f"(d[21]), "+f"(d[22]), "+f"(d[23]),
        "+f"(d[24]), "+f"(d[25]), "+f"(d[26]), "+f"(d[27]), "+f"(d[28]), "+f"(d[29]), "+f"(d[30]), "+f"(d[31]),
        "+f"(d[32]), "+f"(d[33]), "+f"(d[34]), "+f"(d[35]), "+f"(d[36]), "+f"(d[37]), "+f"(d[38]), "+f"(d[39]),
        "+f"(d[40]), "+f"(d[41]), "+f"(d[42]), "+f"(d[43]), "+f"(d[44]), "+f"(d[45]), "+f"(d[46]), "+f"(d[47]),
        "+f"(d[48]), "+f"(d[49]), "+f"(d[50]), "+f"(d[51]), "+f"(d[52]), "+f"(d[53]), "+f"(d[54]), "+f"(d[55]),
        "+f"(d[56]), "+f"(d[57]), "+f"(d[58]), "+f"(d[59]), "+f"(d[60]), "+f"(d[61]), "+f"(d[62]), "+f"(d[63])
      : "l"(da), "l"(db), "r"(sc));
}

__device__ __forceinline__ void wgmma_ss_n40(float (&d)[20], uint64_t da, uint64_t db, int sc) {
  asm volatile("{\n.reg .pred p;\nsetp.ne.b32 p, %22, 0;\n"
      "wgmma.mma_async.sync.aligned.m64n40k16.f32.bf16.bf16 "
      "{%0,%1,%2,%3,%4,%5,%6,%7,%8,%9,%10,%11,%12,%13,%14,%15,%16,%17,%18,%19}, "
      "%20, %21, p, 1, 1, 1, 1;\n}\n"
      : "+f"(d[0]), "+f"(d[1]), "+f"(d[2]), "+f"(d[3]), "+f"(d[4]), "+f"(d[5]), "+f"(d[6]), "+f"(d[7]),
        "+f"(d[8]), "+f"(d[9]), "+f"(d[10]), "+f"(d[11]), "+f"(d[12]), "+f"(d[13]), "+f"(d[14]), "+f"(d[15]),
        "+f"(d[16]), "+f"(d[17]), "+f"(d[18]), "+f"(d[19])
      : "l"(da), "l"(db), "r"(sc));
}

__device__ __forceinline__ void wgmma_rs_n8(float (&d)[4], const uint4& a, uint64_t db, int sc) {
  asm volatile("{\n.reg .pred p;\nsetp.ne.b32 p, %9, 0;\n"
      "wgmma.mma_async.sync.aligned.m64n8k16.f32.bf16.bf16 "
      "{%0,%1,%2,%3}, "
      "{%4,%5,%6,%7}, %8, p, 1, 1, 1;\n}\n"
      : "+f"(d[0]), "+f"(d[1]), "+f"(d[2]), "+f"(d[3])
      : "r"(a.x), "r"(a.y), "r"(a.z), "r"(a.w), "l"(db), "r"(sc));
}

__device__ __forceinline__ void wgmma_rs_n16(float (&d)[8], const uint4& a, uint64_t db, int sc) {
  asm volatile("{\n.reg .pred p;\nsetp.ne.b32 p, %13, 0;\n"
      "wgmma.mma_async.sync.aligned.m64n16k16.f32.bf16.bf16 "
      "{%0,%1,%2,%3,%4,%5,%6,%7}, "
      "{%8,%9,%10,%11}, %12, p, 1, 1, 1;\n}\n"
      : "+f"(d[0]), "+f"(d[1]), "+f"(d[2]), "+f"(d[3]), "+f"(d[4]), "+f"(d[5]), "+f"(d[6]), "+f"(d[7])
      : "r"(a.x), "r"(a.y), "r"(a.z), "r"(a.w), "l"(db), "r"(sc));
}

__device__ __forceinline__ void wgmma_rs_n24(float (&d)[12], const uint4& a, uint64_t db, int sc) {
  asm volatile("{\n.reg .pred p;\nsetp.ne.b32 p, %17, 0;\n"
      "wgmma.mma_async.sync.aligned.m64n24k16.f32.bf16.bf16 "
      "{%0,%1,%2,%3,%4,%5,%6,%7,%8,%9,%10,%11}, "
      "{%12,%13,%14,%15}, %16, p, 1, 1, 1;\n}\n"
      : "+f"(d[0]), "+f"(d[1]), "+f"(d[2]), "+f"(d[3]), "+f"(d[4]), "+f"(d[5]), "+f"(d[6]), "+f"(d[7]),
        "+f"(d[8]), "+f"(d[9]), "+f"(d[10]), "+f"(d[11])
      : "r"(a.x), "r"(a.y), "r"(a.z), "r"(a.w), "l"(db), "r"(sc));
}

struct Params {
  const __nv_bfloat16 *logA, *Aim, *Cre, *Cim, *logdt, *Dskip, *x, *wphi, *wo;
  __nv_bfloat16* out;
  uint4* xs;
  long long* ts;
};

__device__ __forceinline__ uint4 tr_row(const uint4 (&v)[8], int i) {
  uint32_t o[4];
#pragma unroll
  for (int m = 0; m < 4; m++) {
    const uint4 &ra = v[2 * m], &rb = v[2 * m + 1];
    const int k = i >> 1;
    const uint32_t xa = k == 0 ? ra.x : k == 1 ? ra.y : k == 2 ? ra.z : ra.w;
    const uint32_t xb = k == 0 ? rb.x : k == 1 ? rb.y : k == 2 ? rb.z : rb.w;
    o[m] = __byte_perm(xa, xb, (i & 1) ? 0x7632 : 0x5410);
  }
  return make_uint4(o[0], o[1], o[2], o[3]);
}

struct cpx { float r, i; };
__device__ __forceinline__ cpx csq(cpx a) { return {a.r * a.r - a.i * a.i, 2.f * (a.r * a.i)}; }
__device__ __forceinline__ cpx polar(float e, float t) {
  const float m = ex2(e);
  return {m * __cosf(t), m * __sinf(t)};
}

struct KgenRaw { unsigned short la, ai, cr, ci, ldt; };
__device__ __forceinline__ KgenRaw kgen_load(const Params& P, int d, int unit, int lane) {
  const int o = d * 128 + unit * 32 + lane;
  return {__ldg((const unsigned short*)P.logA + o), __ldg((const unsigned short*)P.Aim + o), __ldg((const unsigned short*)P.Cre + o),
          __ldg((const unsigned short*)P.Cim + o), __ldg((const unsigned short*)P.logdt + d)};
}
struct hmul { __half2 a, b; };
__device__ __forceinline__ hmul mk_mul(cpx w) {
  uint32_t b;
  asm("{\n.reg .f32 n;\nneg.ftz.f32 n, %1;\ncvt.rn.f16x2.f32 %0, %2, n;\n}\n" : "=r"(b) : "f"(w.i), "f"(w.r));
  return {__floats2half2_rn(w.r, w.i), *(const __half2*)&b};
}
__device__ __forceinline__ __half2 hcm(__half2 z, const hmul& w) { return __hfma2(__high2half2(z), w.b, __hmul2(__low2half2(z), w.a)); }
__device__ __forceinline__ uint32_t hu(__half2 v) { return *(const uint32_t*)&v; }

struct KgenAddr { uint32_t sa, sb, lb, lc, la; };
__device__ __forceinline__ KgenAddr kgen_addr(int lane, uint32_t buf) {
  KgenAddr a;
  a.sa = buf + (lane & 7) * 128 + ((((lane >> 3) ^ lane) & 7) << 4);
  a.lb = buf + (lane >> 3) * 128 + (((lane ^ (lane >> 3)) & 7) << 4);
  a.la = buf + ((lane >> 3) & 1) * 1024 + (lane >> 4) * 128 + (((lane ^ (lane >> 4)) & 7) << 4);
  a.sb = a.sa ^ 64; a.lc = a.lb ^ 64;
  asm volatile("" : "+r"(a.sa), "+r"(a.sb), "+r"(a.lb), "+r"(a.lc), "+r"(a.la));
  return a;
}
__device__ __forceinline__ void kgen_unit(const KgenRaw& r, const KgenAddr& ad, uint32_t zero, float (&k)[5][4], float& k2048, float& sc) {
  const float dt = bf_round(expf(bf_lo(r.ldt)));
  const float a2 = bf_round(ex2(bf_lo(r.la) * 1.4426950408889634f)) * (dt * -1.4426950408889634f);
  const float f = bf_lo(r.ai) * dt;
  const float r128 = f * 20.371832715762604f;
  const uint32_t ex = min(max(__reduce_max_sync(0xffffffffu, max(r.cr & 0x7fffu, r.ci & 0x7fffu)) >> 7, 1u), 253u);
  const float cs = uf((254u - ex) << 23);
  sc = 2.f * dt * uf(ex << 23);
  const cpx C = {bf_lo(r.cr) * cs, -bf_lo(r.ci) * cs};
  auto put = [&](const __half2 (&v)[8], uint32_t off) {
    stsm4(ad.sa + off, hu(v[0]), hu(v[1]), hu(v[2]), hu(v[3]));
    stsm4(ad.sb + off, hu(v[4]), hu(v[5]), hu(v[6]), hu(v[7]));
  };
  uint32_t A[4][4], B[5][2][4];
  auto get = [&](int j, uint32_t off) {
    __syncwarp();
    ldsm4(B[j][0], ad.lb + off);
    ldsm4(B[j][1], ad.lc + 512 + off);
  };
  auto tile = [&](int j) {
    k[j][0] = k[j][1] = k[j][2] = k[j][3] = 0.f;
#pragma unroll
    for (int s = 0; s < 4; s++) mma_h(k[j], A[s], B[j][s >> 1][2 * (s & 1)], B[j][s >> 1][2 * (s & 1) + 1]);
  };
  auto after = [&](cpx v, uint32_t dep) { return cpx{uf(fu(v.r) ^ (dep & zero)), v.i}; };
  const cpx w1 = polar(a2, f), w128 = polar(a2 * 128.f, (r128 - rintf(r128)) * 6.283185307179586f);
  const cpx w2 = csq(w1), w4 = csq(w2);
  __half2 t0[8], t1[8], t2[8], t3[8], t4[8];
  const hmul m2 = mk_mul(w2), m4 = mk_mul(w4), m128 = mk_mul(w128);
  t0[0] = __floats2half2_rn(1.f, 0.f); t0[1] = __floats2half2_rn(w1.r, w1.i); t0[2] = m2.a; t0[4] = m4.a;
  t0[3] = hcm(t0[1], m2); t0[5] = hcm(t0[1], m4); t0[6] = hcm(t0[2], m4); t0[7] = hcm(t0[3], m4);
  put(t0, 0); get(0, 0);
  t1[0] = m128.a;
#pragma unroll
  for (int i = 1; i < 8; i++) t1[i] = hcm(t0[i], m128);
  put(t1, 1024); get(1, 1024);
  {
    cpx w8 = csq(after(w4, B[0][0][0]));
    w8.i = -w8.i;
    const cpx w16 = csq(w8), w32 = csq(w16), w64 = csq(w32);
    const hmul m8 = mk_mul(w8), m16 = mk_mul(w16), m32 = mk_mul(w32), m64 = mk_mul(w64);
    __half2 a[8];
    a[0] = __floats2half2_rn(C.r, C.i); a[1] = hcm(a[0], m8);
    a[2] = hcm(a[0], m16); a[3] = hcm(a[1], m16);
#pragma unroll
    for (int i = 0; i < 4; i++) a[4 + i] = hcm(a[i], m32);
    put(a, 0);
#pragma unroll
    for (int i = 0; i < 8; i++) a[i] = hcm(a[i], m64);
    put(a, 1024);
    __syncwarp();
#pragma unroll
    for (int s = 0; s < 4; s++) ldsm4(A[s], (ad.la ^ (s << 5)) + s * 256);
  }
  const cpx w256 = csq(after(w128, B[1][0][0]));
  const hmul m256 = mk_mul(w256);
  t2[0] = m256.a;
#pragma unroll
  for (int i = 1; i < 8; i++) t2[i] = hcm((i & 1) ? t1[i & 6] : t0[i & 6], m256);
  put(t2, 0); get(2, 0);
  tile(0); tile(1);
  const cpx w512 = csq(after(w256, A[0][0]));
  const hmul m512 = mk_mul(w512);
  t3[0] = m512.a;
#pragma unroll
  for (int i = 1; i < 8; i++) t3[i] = hcm((i & 2) ? t2[i & 5] : ((i & 1) ? t1[i & 4] : t0[i & 4]), m512);
  put(t3, 1024); get(3, 1024);
  tile(2);
  const cpx w1024 = csq(after(w512, B[2][0][0])), we = csq(w1024);
  const hmul m1024 = mk_mul(w1024);
  t4[0] = m1024.a;
#pragma unroll
  for (int i = 1; i < 8; i++) t4[i] = hcm((i & 4) ? t3[i & 3] : ((i & 2) ? t2[i & 1] : t1[0]), m1024);
  put(t4, 0); get(4, 0);
  tile(3); tile(4);
  k2048 = (C.r * we.r + C.i * we.i) * sc;
}

__device__ __forceinline__ void build_tables(uint32_t tb, int lane, float (&k)[5][4], float k2048) {
  const int g = lane >> 2, c = lane & 3;
  const uint32_t kc = tb + T_KC + 16;
  {
    const uint32_t a0 = kc + 16 * g + 4 * c, a2 = kc + 2 * (256 + 4 * g + c);
    const uint32_t a3 = kc + 2 * (384 + 2 * g + 64 * (c & 1) + (c >> 1)), a4 = kc + 2 * (512 + g + 32 * c);
#pragma unroll
    for (int r = 0; r < 2; r++) {
      sts32(a0 + 128 * r, pack_bf(k[0][2 * r], k[0][2 * r + 1]));
      sts32(a0 + 128 * r + 256, pack_bf(k[1][2 * r], k[1][2 * r + 1]));
      const uint32_t w2 = pack_bf(k[2][2 * r], k[2][2 * r + 1]);
      const uint32_t w3 = pack_bf(k[3][2 * r], k[3][2 * r + 1]);
      const uint32_t w4 = pack_bf(k[4][2 * r], k[4][2 * r + 1]);
      sts16(a2 + 64 * r, w2); sts16(a2 + 64 * r + 128, w2 >> 16);
      sts16(a3 + 32 * r, w3); sts16(a3 + 32 * r + 64, w3 >> 16);
      sts16(a4 + 16 * r, w4); sts16(a4 + 16 * r + 32, w4 >> 16);
    }
  }
  if (lane == 0) { sts16(kc + 2 * 640, pack_bf(k2048, 0.f)); sts32(kc - 4, 0); }
  __syncwarp();
  const uint32_t td = tb + T_D + 32;
#pragma unroll
  for (int hf = 0; hf < 2; hf++) {
    const uint2 v = lds64(kc + 256 * hf + 8 * lane);
    const uint32_t pv = lds32(kc + 256 * hf + 8 * lane - 4);
    sts128(td + 512 * hf + 16 * lane, __byte_perm(v.x, pv, 0x7610), __byte_perm(v.x, v.x, 0x1032), __byte_perm(v.y, v.x, 0x7610),
           __byte_perm(v.y, v.y, 0x1032));
  }
#pragma unroll
  for (int hf = 0; hf < 2; hf++) {
    const uint32_t v = lds32(kc + 512 + 128 * hf + 4 * lane), nx = lds32(kc + 516 + 128 * hf + 4 * lane);
    uint32_t w0 = __byte_perm(v, v, 0x1010);
    const uint32_t w1 = w0;
    if (hf == 0) { const uint32_t pv = lds32(kc + 508); if (lane == 0) w0 = __byte_perm(v, pv, 0x7610); }
    sts128(td + 1024 + 512 * hf + 16 * lane, w0, w1, __byte_perm(v, v, 0x1032), __byte_perm(nx, v, 0x7610));
  }
  {
    const uint32_t kk = lds16(kc + 2 * 384);
    const uint32_t w = lane < 3 ? (kk | (kk << 16)) : (lane == 3 ? (kk << 16) : 0u);
    if (lane < 24) sts32(td + 4 * (lane < 16 ? 512 + lane : lane - 24), w);
    const uint32_t lo_ = lds16(kc + 2 * 511), le_ = lds16(kc + 2 * 512);
    const uint32_t ja = tb + T_5 + (lane < 16 ? 4 * lane : 256 + 4 * lane);
    sts32(ja, lane == 16 ? (le_ << 16) : 0u);
    sts32(ja + 384, lane == 16 ? (lo_ << 16) : 0u);
    sts32(tb + (lane < 16 ? T_7 : T_9 - 64) + 4 * lane, 0u);
  }
#pragma unroll
  for (int s = 0; s < 2; s++) {
    const uint32_t b = kc + 2 * (s ? 512 : 384) + 8 * lane;
    const uint2 v = lds64(b);
    uint32_t em = lds16(b - 2), e0 = v.x;
    const uint32_t e4 = lds16(b + 8);
    if (lane == 0) { em = 0; e0 = 0; }
    sts64(tb + (s ? T_7 : T_3) + 64 + 8 * lane, __byte_perm(v.x, em, 0x5432), __byte_perm(v.y, v.x, 0x7632));
    sts64(tb + (s ? T_9 : T_5) + 64 + 8 * lane, __byte_perm(v.y, e0, 0x5410), __byte_perm(e4, v.y, 0x5410));
  }
  __syncwarp();
}

__device__ __forceinline__ uint32_t box2w(int lo, int n, int o) {
  return ((unsigned)(o - lo) < (unsigned)n ? 0x3F80u : 0u) | ((unsigned)(o + 1 - lo) < (unsigned)n ? 0x3F800000u : 0u);
}

__device__ __forceinline__ void conv_channel(uint32_t ub, uint32_t tb, int lane, uint4* ydst) {
  const int g = lane >> 2, c = lane & 3, x = g - 2 * c;
  const int mi = lane >> 3;
  const uint32_t qa = ub + U_PAD + 16 * (lane & 7) + ((mi == 0 || mi == 3) ? U_ODD : 0) - (mi == 0 ? 16 : 0);
  const uint32_t hb = ub + U_PAD + (mi & 1) * U_ODD + 16 * ((lane >> 4) + (lane & 7)) - 16;
  const uint32_t kv = lds16(tb + T_KC + 16 + 2 * 512);
  const int oh = c < 2 ? 8 + 2 * c : 2 * c - 8, og = c < 3 ? 2 * c : -10;
  uint32_t bx[4] = {box2w(g - 4, 9, 2 * c), box2w(g - 3, 7, 2 * c), box2w(g - 4, 9, oh), box2w(g - 3, 7, oh)};
  uint32_t by[4] = {box2w(g - 10, 5, 2 * c - 8), box2w(g - 5, 3, 2 * c - 8), box2w(g - 10, 5, og), box2w(g - 5, 3, og)};
  uint32_t lb0 = ((unsigned)(x + 5) < 2u ? kv : 0u) | ((unsigned)(x + 4) < 2u ? kv << 16 : 0u);
  uint32_t lb1 = ((unsigned)(x - 3) < 2u ? kv : 0u) | ((unsigned)(x - 4) < 2u ? kv << 16 : 0u);
  const int q0 = g - 1, q1 = c < 3 ? g : g - 2;
  uint32_t y0a = ub + U_PAD + (q0 & 1) * U_ODD + 16 * (q0 >> 1) + 4 * c;
  uint32_t y1a = ub + U_PAD + (q1 & 1) * U_ODD + 16 * (q1 >> 1) + 4 * c;
#pragma unroll
  for (int i = 0; i < 4; i++) asm volatile("" : "+r"(bx[i]), "+r"(by[i]));
  asm volatile("" : "+r"(lb0), "+r"(lb1), "+r"(y0a), "+r"(y1a));
  mbar_wait(BAR(MB_UFULL));
  mbar_wait(BAR(MB_EMPTY + 15));
  TS(36);
  float acc[16][4];
  {
    uint32_t z09[8], z07[8], zm9[8], zm7[8];
#pragma unroll
    for (int i = 0; i < 8; i++) {
      uint32_t h[4];
      ldsm4(h, hb + 128 * i);
      float y0, y1, y2, y3, w0, w1, w2, w3;
      mma0(y0, y1, y2, y3, bx[0], bx[1], bx[2], bx[3], h[2], c < 2 ? h[3] : h[1]);
      mma0(w0, w1, w2, w3, bx[0], bx[1], bx[2], bx[3], h[1], c < 2 ? h[2] : h[0]);
      z09[i] = pack_bf(y0, y1); z07[i] = pack_bf(y2, y3);
      zm9[i] = pack_bf(w0, w1); zm7[i] = pack_bf(w2, w3);
    }
  uint32_t f3[3][4][4];
  {
    const uint32_t fa = tb + T_7 + 4 * (16 + x);
#pragma unroll
    for (int tt = 0; tt < 3; tt++)
#pragma unroll
      for (int D = 0; D < 4; D++) {
        const uint32_t a = fa + (tt == 0 ? 316 : (tt == 1 ? 320 : 0)) + 64 * D;
        f3[tt][D][0] = lds32(a); f3[tt][D][1] = lds32(a + 32); f3[tt][D][2] = lds32(a - 32); f3[tt][D][3] = lds32(a);
      }
  }
    float a[4][2][4];
#pragma unroll
    for (int kap = 0; kap < 4; kap++)
#pragma unroll
      for (int sg = 0; sg < 2; sg++)
#pragma unroll
        for (int bk = 3; bk >= kap; bk--) {
          const uint32_t(&q0_)[4] = f3[sg ? 2 : 0][bk - kap];
          const uint32_t(&q1_)[4] = f3[sg ? 2 : 1][bk - kap];
          float(&a0)[4] = a[bk][0];
          float(&a1)[4] = a[bk][1];
          if (sg == 0 && kap == 0) {
            mma0(a0[0], a0[1], a0[2], a0[3], q0_[0], q0_[1], q0_[2], q0_[3], z09[0], z09[1]);
            mma0(a1[0], a1[1], a1[2], a1[3], q1_[0], q1_[1], q1_[2], q1_[3], zm9[0], zm9[1]);
          } else {
            mma(a0[0], a0[1], a0[2], a0[3], q0_[0], q0_[1], q0_[2], q0_[3], sg ? zm7[2 * kap] : z09[2 * kap], sg ? zm7[2 * kap + 1] : z09[2 * kap + 1]);
            mma(a1[0], a1[1], a1[2], a1[3], q1_[0], q1_[1], q1_[2], q1_[3], sg ? z07[2 * kap] : zm9[2 * kap], sg ? z07[2 * kap + 1] : zm9[2 * kap + 1]);
          }
        }
    SPLIT();
#pragma unroll
    for (int i = 0; i < 8; i++) {
      uint32_t h[4];
      ldsm4(h, qa + 128 * i);
      const float ci[4] = {a[i >> 1][0][2 * (i & 1)], a[i >> 1][0][2 * (i & 1) + 1], a[i >> 1][1][2 * (i & 1)], a[i >> 1][1][2 * (i & 1) + 1]};
      mmac(acc[8 + i], h[0], h[1], h[2], h[3], lb0, lb1, ci);
    }
  }
  TS(44);
  {
    uint2 a5[10], a3[10];
    const uint32_t aa = tb + T_5 + 4 * (8 + 2 * g - 2 * c);
#pragma unroll
    for (int m = 0; m < 10; m++) { a5[m] = lds64(aa + 32 * m); a3[m] = lds64(aa + 384 + 32 * m); }
    uint32_t x5[12][2], x3[12][2];
    auto ygen = [&](int kap) {
#pragma unroll
      for (int hh = 0; hh < 2; hh++) {
        float y0, y1, y2, y3;
        mma0(y0, y1, y2, y3, by[0], by[1], by[2], by[3], lds32(y0a + 128 * kap + 64 * hh), lds32(y1a + 128 * kap + 64 * hh));
        x5[kap][hh] = pack_bf(y0, y1);
        x3[kap][hh] = pack_bf(y2, y3);
      }
    };
    ygen(11); ygen(10); ygen(9); ygen(8);
#pragma unroll
    for (int kap = 11; kap >= 0; kap--) {
      if (kap >= 4) ygen(kap - 4);
#pragma unroll
      for (int sg = 0; sg < 2; sg++)
#pragma unroll
        for (int i = 4; i >= 0; i--) {
          const int be = kap + 4 + i;
          if (be <= 15) {
            const uint2 &hi = sg ? a3[2 * i + 1] : a5[2 * i + 1], &lo = sg ? a3[2 * i] : a5[2 * i];
            const uint32_t b0 = sg ? x3[kap][0] : x5[kap][0], b1 = sg ? x3[kap][1] : x5[kap][1];
            if (be < 8 && i == 0 && sg == 0) mma0(acc[be][0], acc[be][1], acc[be][2], acc[be][3], hi.x, hi.y, lo.x, lo.y, b0, b1);
            else mma(acc[be][0], acc[be][1], acc[be][2], acc[be][3], hi.x, hi.y, lo.x, lo.y, b0, b1);
          }
        }
    }
  }
  TS(45);
  {
    const uint32_t st = tb + T_ST + lane * 8;
#pragma unroll
    for (int be = 4; be < 12; be++) sts64(st + 256 * be, pack_bf(acc[be][0], acc[be][1]), pack_bf(acc[be][2], acc[be][3]));
    SPLIT();
    uint32_t F[66], qd[8][4];
    const uint32_t fa = tb + T_D + 32 + 4 * x;
#pragma unroll
    for (int i = 0; i < 32; i++) {
      const int s = 120 - (i >> 2) - 8 * (i & 3);
      uint32_t(&q)[4] = qd[i & 7];
      ldsm4(q, qa + 16 * s);
      const int m = 16 * (i & 3) + 2 * (i >> 2);
      F[m] = lds32(fa + 32 * m); F[m + 1] = lds32(fa + 32 * m + 32);
#pragma unroll
      for (int be = 15; be >= 12; be--) {
        const int de = 8 * be - s;
        float(&a)[4] = (be >= 14 && !(i & 1)) ? acc[be - 4] : acc[be];
        if (de >= 0 && be >= 14 && i == 2 * (15 - be)) mma0(a[0], a[1], a[2], a[3], q[0], q[1], q[2], q[3], F[2 * de + 1], F[2 * de]);
        else if (de >= 0) mma(a[0], a[1], a[2], a[3], q[0], q[1], q[2], q[3], F[2 * de + 1], F[2 * de]);
      }
    }
#pragma unroll
    for (int i = 0; i < 8; i++) acc[14 + (i >> 2)][i & 3] += acc[10 + (i >> 2)][i & 3];
    F[64] = lds32(fa + 32 * 64); F[65] = lds32(fa + 32 * 65);
    uint32_t qp = qa + 128 * 11, sta = st + 256 * 10;
    uint4* yd = ydst + 7 * 32;
#pragma unroll
    for (int i = 0; i < 6; i++) ldsm4(qd[i], qp - 16 * i);
    uint2 sv = lds64(sta + 256);
    float ci[4] = {bf_lo(sv.x), bf_hi(sv.x), bf_lo(sv.y), bf_hi(sv.y)};
    float T[5][4];
#pragma unroll
    for (int i = 0; i < 16; i++) T[i >> 2][i & 3] = acc[12 + (i >> 2)][i & 3];
    nb_sync(NB_YZ, 160);
    TS(46);
#pragma unroll 1
    for (int bp = 5; bp >= 0; bp--) {
      uint32_t held[2];
#pragma unroll
      for (int o = 1; o >= 0; o--) {
#pragma unroll
        for (int k = 4; k >= 1; k--) mmac(T[k], qd[0][0], qd[0][1], qd[0][2], qd[0][3], F[16 * k + 1], F[16 * k], T[k - 1]);
        mmac(T[0], qd[0][0], qd[0][1], qd[0][2], qd[0][3], F[1], F[0], ci);
        ldsm4(qd[6], qp - 16 * 6);
        ldsm4(qd[7], qp - 16 * 7);
        sv = lds64(sta);
#pragma unroll
        for (int i = 1; i < 8; i++) {
#pragma unroll
          for (int k = 3; k >= 0; k--)
            mma(T[k][0], T[k][1], T[k][2], T[k][3], qd[i][0], qd[i][1], qd[i][2], qd[i][3], F[16 * k + 2 * i + 1], F[16 * k + 2 * i]);
          if (i < 7) ldsm4(qd[i - 1], qp - 128 - 16 * (i - 1));
          if (i == 2) {
            const uint32_t w0 = pack_bf(T[4][0], T[4][1]), w1 = pack_bf(T[4][2], T[4][3]);
            if (o) { held[0] = w0; held[1] = w1; }
            else st_x(yd, nz(w0), w1, held[0], held[1]);
          }
          if (i == 4) {
            if (2 * bp + o <= 4) sv = make_uint2(0, 0);
            ci[0] = bf_lo(sv.x); ci[1] = bf_hi(sv.x); ci[2] = bf_lo(sv.y); ci[3] = bf_hi(sv.y);
          }
        }
        qp -= 128; sta -= 256;
      }
      yd -= 32;
    }
#pragma unroll
    for (int B = 1; B >= 0; B--)
      st_x(ydst + B * 32, nz(pack_bf(T[2 * B][0], T[2 * B][1])), pack_bf(T[2 * B][2], T[2 * B][3]),
           pack_bf(T[2 * B + 1][0], T[2 * B + 1][1]), pack_bf(T[2 * B + 1][2], T[2 * B + 1][3]));
  }
}

__device__ __forceinline__ void dual_exp(const uint32_t* w, uint32_t* e) {
  const float L = 1.44268798828125f;
  uint32_t mx = bmax2(bmax2(w[0], w[1]), bmax2(w[2], w[3]));
  uint32_t mn = bmin2(bmin2(w[0], w[1]), bmin2(w[2], w[3]));
  mx = bmax2(mx, __shfl_xor_sync(0xffffffffu, mx, 1));
  mn = bmin2(mn, __shfl_xor_sync(0xffffffffu, mn, 1));
  mx = bmax2(mx, __shfl_xor_sync(0xffffffffu, mx, 2));
  mn = bmin2(mn, __shfl_xor_sync(0xffffffffu, mn, 2));
  const float mx0 = bf_lo(mx) * -L, mx1 = bf_hi(mx) * -L, mn0 = bf_lo(mn) * L, mn1 = bf_hi(mn) * L;
#pragma unroll
  for (int i = 0; i < 2; i++) {
    const float a0 = bf_lo(w[2 * i]), a1 = bf_hi(w[2 * i]), b0 = bf_lo(w[2 * i + 1]), b1 = bf_hi(w[2 * i + 1]);
    e[2 * i] = pack_bf(ex2(fmaf(a0, L, mx0)), ex2(fmaf(b0, L, mx0)));
    e[2 * i + 1] = pack_bf(ex2(fmaf(a1, L, mx1)), ex2(fmaf(b1, L, mx1)));
    e[4 + 2 * i] = pack_bf(ex2(fmaf(a0, -L, mn0)), ex2(fmaf(b0, -L, mn0)));
    e[5 + 2 * i] = pack_bf(ex2(fmaf(a1, -L, mn1)), ex2(fmaf(b1, -L, mn1)));
  }
}
__device__ __forceinline__ void normalise(uint32_t* e, const float (&s)[4]) {
  const uint32_t r = pack_bf(rcp(s[0]), rcp(s[2]));
  const __nv_bfloat162 rr = *(const __nv_bfloat162*)&r;
#pragma unroll
  for (int i = 0; i < 4; i++) {
    const __nv_bfloat162 v = __hmul2(*(const __nv_bfloat162*)&e[i], (i & 1) ? __high2bfloat162(rr) : __low2bfloat162(rr));
    e[i] = *(const uint32_t*)&v;
  }
}
__host__ __device__ constexpr uint64_t qdesc(uint32_t addr) { return mkdesc(addr, 128, 256, 0); }

__global__ void __launch_bounds__(NTHREADS, 1)
fused_kernel(const Params P, const __grid_constant__ CUtensorMap mx, const __grid_constant__ CUtensorMap mw,
             const __grid_constant__ CUtensorMap mo, const __grid_constant__ CUtensorMap mu,
             const __grid_constant__ CUtensorMap mout, const __grid_constant__ CUtensorMap mw4) {
  constexpr uint32_t sb = SB;
  const int tid = threadIdx.x, lane = tid & 31;
  const int warp = __shfl_sync(0xffffffffu, tid >> 5, 0);
  const int b = blockIdx.x, oct = b >> 3, i8 = b & 7;
  const int rt = oct < 8 ? oct : 15 - oct;
  const int hp = (oct >> 3) * 8 + i8;

  const int wg = warp >> 2, w = warp & 3;
  const int d = b * 4 + ((tid >> 5) & 3);
  if (tid < 384) {
    asm volatile("prefetch.tensormap [%0];" ::"l"(&mu) : "memory");
    asm volatile("prefetch.tensormap [%0];" ::"l"(&mw) : "memory");
    asm volatile("prefetch.tensormap [%0];" ::"l"(&mx) : "memory");
    asm volatile("prefetch.tensormap [%0];" ::"l"(&mw4) : "memory");
  }
  if (warp == 12) {
    if (lane == 0) {
#pragma unroll
      for (int i = 0; i < 9; i++) mbar_init(BAR(i), 1);
      asm volatile("fence.mbarrier_init.release.cluster;" ::: "memory");
    }
    __syncwarp();
    if (lane < 9) mbar_expect(BAR(0) + 8 * lane, lane == 5 ? 65536 : ((lane == 0 || lane > 5) ? 16384 : 28672));
    __syncwarp();
    e_tma3d(sb + OFF_W, &mw, BAR(MB_FULL), hp * 32, 0, 0);
    e_tma2d(sb + OFF_X + 3 * 16384, &mx, BAR(MB_FULL), 0, rt * 256);
    nb_arrive(NB_PROD, 192);
  } else if (warp == 13) {
    if (lane == 0) {
#pragma unroll
      for (int i = 9; i < 39; i++) mbar_init(BAR(i), i < MB_EMPTY ? 1 : (i < MB_AUX ? 4 : 8));
      asm volatile("fence.mbarrier_init.release.cluster;" ::: "memory");
    }
    __syncwarp();
    if (lane < 9) mbar_expect(BAR(MB_FULL + 8) + 8 * lane, lane < 8 ? 16384 : 131072);
    nb_arrive(NB_PROD, 192);
  }
  const KgenRaw raw = kgen_load(P, d, tid >> 7, lane);
  const unsigned short dsk = __ldg((const unsigned short*)P.Dskip + d);
  const uint32_t tb = sb + OFF_T + w * T_CH;
  const uint32_t kp = wg >= 2 ? sb + OFF_STG0 + 16384 + w * 2048 : ((tb + 127) & ~127u) + wg * 2048;
  const KgenAddr kad = kgen_addr(lane, wg == 3 ? sb + OFF_X + 32768 + w * 2048 : kp);
  if (wg == 1) nb_sync(NB_PROD, 192);
  if (warp == 12) {
#pragma unroll 1
    for (int kb = 1; kb < 4; kb++) {
      if (kb == U_AT) e_tma4d(sb + OFF_STG0, &mu, BAR(MB_URAW), i8 * 64, oct * 2);
      e_tma3d(sb + OFF_W + kb * 12288, &mw, BAR(MB_FULL) + 8 * kb, hp * 32, kb * 64, 0);
      e_tma2d(sb + OFF_X + (kb < 2 ? kb + 3 : kb - 2) * 16384, &mx, BAR(MB_FULL) + 8 * kb, kb * 64, rt * 256);
    }
    e_prefetch(P.x + (size_t)(rt * 256 + hp * 16) * 512, 16384);
    e_tma4d(sb + OFF_W + 4 * 12288, &mw4, BAR(MB_FULL + 4), hp * 32, 4);
    if (smem_u32(smem_raw) != SB) __trap();
    if (lane == 0) TS1(54);
  }
  float k[5][4], k2048, ksc;
  kgen_unit(raw, kad, blockIdx.y, k, k2048, ksc);
  TS(40 + wg);
  if ((fu(k[0][0]) & fu(k[1][0]) & fu(k[2][0]) & fu(k[3][0]) & fu(k[4][0])) == 0xffffffffu) sts32(kp, 0);
  if (wg == 3) {
    nb_sync(0, 512);
    if (warp == 12) {
      asm volatile("fence.proxy.async.shared::cta;" ::: "memory");
      e_tma2d(sb + OFF_X + 2 * 16384, &mx, BAR(MB_FULL + 4), 256, rt * 256);
    }
  } else if (wg) {
    nb_arrive(0, 512);
  }
  k2048 += __shfl_xor_sync(0xffffffffu, k2048, 16);
  k2048 += __shfl_xor_sync(0xffffffffu, k2048, 8);
  if (wg != 2) {
    uint32_t h[10];
#pragma unroll
    for (int j = 0; j < 10; j++) h[j] = hu(__floats2half2_rn(k[j >> 1][2 * (j & 1)], k[j >> 1][2 * (j & 1) + 1]));
    sts128(kp + lane * 16, h[0], h[1], h[2], h[3]);
    sts128(kp + 512 + lane * 16, h[4], h[5], h[6], h[7]);
    sts128(kp + 1024 + lane * 16, h[8], h[9], fu(k2048), fu(ksc));
  }
  if (wg == 0) { nb_arrive(NB_PREP, 512); nb_sync(0, 512); }
  else if (wg != 2) nb_arrive(NB_PREP, 512);
  else nb_sync(NB_PREP, 512);
  if (warp >= 12) {
    asm volatile("setmaxnreg.dec.sync.aligned.u32 32;");
    if (warp == 12) {
      uint32_t slot = sb + OFF_X + 3 * 16384;
#pragma unroll 1
      for (int n = 0; n < 11; n++) {
        mbar_spin(BAR(MB_EMPTY) + 8 * n);
        const int m = n + 5;
        e_tma2d(slot, &mx, BAR(MB_FULL) + 8 * m, (m & 7) * 64, rt * 256 + (m >> 3) * 128);
        slot = slot == sb + OFF_X + 4 * 16384 ? sb + OFF_X : slot + 16384;
        if (n == 7) {
          e_prefetch(P.wo + (size_t)b * 2048, 4096);
          asm volatile("prefetch.tensormap [%0];" ::"l"(&mo) : "memory");
          asm volatile("prefetch.tensormap [%0];" ::"l"(&mout) : "memory");
        }
      }
#pragma unroll 1
      for (int i = 0; i < 8; i++) {
        mbar_wait(BAR(MB_EMPTY + 10) + 8 * ((0x54332100u >> (4 * i)) & 7));
        const int w0 = (0x54736210u >> (4 * i)) & 7;
        e_tma3d(sb + OFF_W + w0 * 16384, &mo, BAR(MB_WO), 0, w0 * 64, (hp & 3) * 2);
      }
    } else {
      if (warp == 15) {
        const uint4 v0 = __ldg((const uint4*)P.wphi + hp * 64 + lane), v1 = __ldg((const uint4*)P.wphi + hp * 64 + 32 + lane);
        sts128(sb + OFF_PHI + (lane & 1) * 256 + (lane >> 1) * 16, v0.x, v0.y, v0.z, v0.w);
        sts128(sb + OFF_PHI + 512 + (lane & 1) * 256 + (lane >> 1) * 16, v1.x, v1.y, v1.z, v1.w);
        const uint32_t one = (((lane >> 3) ^ (lane >> 4)) & 1) ? 0u : ((lane & 1) ? 0x3F800000u : 0x3F80u);
        const int q = (lane >> 1) & 3;
        sts128(sb + OFF_EYE + lane * 16, q == 0 ? one : 0u, q == 1 ? one : 0u, q == 2 ? one : 0u, q == 3 ? one : 0u);
        sts64(sb + OFF_ONE + lane * 8, 0x3F803F80u, 0x3F803F80u);
        asm volatile("fence.proxy.async.shared::cta;" ::: "memory");
        nb_arrive(NB_KREAD, 160);
        mbar_wait(BAR(MB_EMPTY + ZERO_STEP));
        uint4* py = P.xs + X_Y + b * 1024 + lane;
#pragma unroll 1
        for (int i = 0; i < 1024; i += 32) st_x(py + i, 0, 0, 0, 0);
        nb_arrive(NB_YZ, 160);
        nb_arrive(NB_ODONE, 320);
        if (lane == 0) TS1(55);
        return;
      }
      uint32_t* const cnt = (uint32_t*)(P.xs + X_CNT) + (warp == 13 ? i8 : 8 + rt) * 32;
      const unsigned target = (ld_x32(cnt) & ~15u) + 16;
      if (warp == 13) {
        uint4* pp = P.xs + X_PART + (hp * 8 + rt) * 144 + lane;
#pragma unroll 1
        for (int i = 0; i < 144; i += 32) if (i + lane < 144) st_x(pp + i, 0, 0, 0, 0);
      }
      nb_sync(warp == 13 ? NB_INIT : NB_ODONE, warp == 13 ? 160 : 320);
      if (lane == 0) TS1(warp == 13 ? 49 : 56);
      asm volatile("fence.proxy.async.shared::cta;" ::: "memory");
      if (lane == 0) asm volatile("red.release.gpu.global.add.u32 [%0], 1;" ::"l"(cnt) : "memory");
      if (lane == 0) TS1(warp == 13 ? 50 : 57);
      const uint32_t* pc = (warp == 13 && (lane & 1)) ? (uint32_t*)(P.xs + X_CNT) + (b >> 4) * 32 : cnt;
#pragma unroll 1
      for (int i = 0; i < SPIN_MAX; i++) {
        unsigned v;
        asm volatile("ld.acquire.gpu.global.u32 %0, [%1];" : "=r"(v) : "l"(pc) : "memory");
        if (__all_sync(0xffffffffu, (int)(v - target) >= 0)) break;
      }
      if (lane == 0) TS1(warp == 13 ? 51 : 58);
      asm volatile("fence.proxy.async.global;" ::: "memory");
      if (warp == 13) {
        mbar_wait(BAR(MB_EMPTY + 11));
        e_expect(BAR(MB_UFULL), 4 * U_CH);
        e_bulk(sb + OFF_U, P.xs + X_UT + b * (U_CH / 4), 4 * U_CH, BAR(MB_UFULL));
      } else {
        const uint4* src = P.xs + X_O + (rt * 4 + (hp >> 2)) * 4096;
        e_expect(BAR(MB_OA), 14336);
        e_bulk(sb + OFF_STG0, src + 3200, 14336, BAR(MB_OA));
        e_expect(BAR(MB_OC), 32768);
        e_bulk(sb + OFF_X + 32768, src, 32768, BAR(MB_OC));
        nb_sync(NB_BDONE, 288);
        asm volatile("fence.proxy.async.shared::cta;" ::: "memory");
        e_expect(BAR(MB_OB), 18432);
        e_bulk(sb + OFF_U, src + 2048, 18432, BAR(MB_OB));
      }
    }
    return;
  }

  const int t = tid & 127;
  const int g = lane >> 2, c = lane & 3;
  {
    if (wg == 2) {
      asm volatile("setmaxnreg.inc.sync.aligned.u32 160;");
#pragma unroll
      for (int j = 0; j < 5; j++) { k[j][0] *= ksc; k[j][1] *= ksc; k[j][2] *= ksc; k[j][3] *= ksc; }
#pragma unroll 1
      for (int q = 0; q < 3; q++) {
        const uint32_t src = (q == 2 ? kp : ((tb + 127) & ~127u) + q * 2048) + lane * 16;
        const uint4 v0 = lds128(src), v1 = lds128(src + 512), v2 = lds128(src + 1024);
        const uint32_t h[10] = {v0.x, v0.y, v0.z, v0.w, v1.x, v1.y, v1.z, v1.w, v2.x, v2.y};
#pragma unroll
        for (int j = 0; j < 10; j++) {
          const float2 f = __half22float2(*(const __half2*)&h[j]);
          k[j >> 1][2 * (j & 1)] = fmaf(f.x, uf(v2.w), k[j >> 1][2 * (j & 1)]);
          k[j >> 1][2 * (j & 1) + 1] = fmaf(f.y, uf(v2.w), k[j >> 1][2 * (j & 1) + 1]);
        }
        k2048 += uf(v2.z);
      }
#pragma unroll
      for (int o2 = 4; o2; o2 >>= 1) k2048 += __shfl_xor_sync(0xffffffffu, k2048, o2);
      if (lane == 0) k[0][0] += bf_lo(dsk);
      __syncwarp();
      if (lane == 0) mbar_arrive(BAR(MB_AUX));
      TS(34);
      build_tables(tb, lane, k, k2048);
      TS(35);
      uint4* const g_y = P.xs + X_Y;
      conv_channel(sb + OFF_U + w * U_CH, tb, lane, g_y + (size_t)d * 256 + lane);
      nb_arrive(NB_BDONE, 288);
      TS(37);
      mbar_wait(BAR(MB_OA));
      const int lam = w * 8 + g;
      const uint4* src = g_y + (size_t)(oct * 32 + c * 8) * 256 + i8 * 32 + lam;
      uint4 v[8];
#pragma unroll 1
      for (int it = 0; it < SPIN_MAX; it++) {
        uint32_t m = 0xffffffffu;
#pragma unroll
        for (int i = 0; i < 8; i++) v[i] = ld_x(src + i * 256);
#pragma unroll
        for (int i = 0; i < 8; i++) m = min(m, v[i].x);
        if (__all_sync(0xffffffffu, m != 0)) break;
      }
      __nv_bfloat16* dst = P.out + (size_t)(i8 * 256 + (lam >> 2) * 16 + (lam & 3) * 2) * 1024 + 512 + oct * 32 + c * 8;
#pragma unroll
      for (int i = 0; i < 8; i++) *(uint4*)(dst + (size_t)((i >> 2) * 128 + ((i >> 1) & 1) * 8 + (i & 1)) * 1024) = tr_row(v, i);
      TS(38);
      GT(63);
      if (w == 0) TSDUMP(32);
      return;
    }
    if (wg == 1) {
      mbar_wait(BAR(MB_URAW));
      TS(48);
      uint4* dst = P.xs + X_UT + (i8 * 64 + g) * (U_CH / 16) + (w & 1) * (U_ODD / 16) + U_PAD / 16 + oct * 8 + (w >> 1) * 4 + c;
      const int ln = ((lane >> 1) & 3) + 4 * (lane & 1);
      uint32_t r[8][4];
#pragma unroll
      for (int i = 0; i < 8; i++) ldsm4t(r[i], sb + OFF_STG0 + w * 4096 + ((lane >> 3) * 8 + ln) * 128 + ((i ^ ln) << 4));
#pragma unroll
      for (int i = 0; i < 8; i++) dst[i * (U_CH / 2)] = make_uint4(r[i][0], r[i][1], r[i][2], r[i][3]);
      nb_arrive(NB_INIT, 160);
      if (lane == 0) mbar_arrive(BAR(MB_AUX));
      mbar_wait(BAR(MB_EMPTY + 4));
      mbar_spin(BAR(MB_EMPTY + 6));
    }
    TS(wg * 16 + 1);
  }

  float acc[2][48];
  {
    uint32_t fb = BAR(MB_FULL) + 64 * wg;
    uint32_t da = (uint32_t)mkdesc(sb + OFF_X, 16, 0, 0) + (wg ? 1024 : 3072), db = (uint32_t)mkdesc(sb + OFF_W, 4096, 0, 0);
    constexpr uint64_t ha = mkdesc(0, 0, 1024, 1), hb = mkdesc(0, 0, 512, 2);
    mbar_spin(fb);
    TS(wg * 16 + 2);
#pragma unroll 1
    for (int kb = 0; kb < 8; kb++) {
      WG_FENCE();
#pragma unroll
      for (int k = 0; k < 4; k++) {
        wgmma_ss_n96(acc[0], ha | (da + 2 * k), hb | (db + 64 * k), k ? 1 : kb);
        wgmma_ss_n96(acc[1], ha | (da + 2 * k + 512), hb | (db + 64 * k), k ? 1 : kb);
      }
      WG_COMMIT();
      if (kb < 7) mbar_spin(fb + 8);
      WG_WAIT(1);
      if (kb > 0) e_arrive(fb + 8 * (MB_EMPTY - MB_FULL - 1));
      fb += 8; db += 768;
      da = da == (uint32_t)mkdesc(sb + OFF_X + 65536, 16, 0, 0) ? da - 4096 : da + 1024;
    }
    if (wg == 0) nb_sync(NB_KREAD, 160);
    WG_WAIT(0);
    e_arrive(fb + 8 * (MB_EMPTY - MB_FULL - 1));
    mbar_spin(fb + 8 * (MB_EMPTY - MB_FULL - 1));
  }
  TS(wg * 16 + 3);
  asm volatile("setmaxnreg.inc.sync.aligned.u32 160;");

  constexpr uint32_t stg0 = sb + OFF_STG0, stg1 = sb + OFF_X + 32768;
  uint4* const g_part = P.xs + X_PART;
  uint4* const g_o = P.xs + X_O;
  constexpr uint32_t kvs = stg0;
  auto pack8 = [](const float* a) { return make_uint4(pack_bf(a[0], a[1]), pack_bf(a[2], a[3]), pack_bf(a[4], a[5]), pack_bf(a[6], a[7])); };
  auto feat = [&](const uint4 (&af)[4], float (&p)[4][8]) {
    WG_FENCE();
#pragma unroll
    for (int u = 0; u < 4; u++) wgmma_rs_n16(p[u], af[u], qdesc(sb + OFF_PHI + (u & 1) * 512), 0);
    WG_COMMIT();
  };
  auto packp = [](const float (&p)[4][8], uint32_t (&pw)[16]) {
#pragma unroll
    for (int i = 0; i < 16; i++) pw[i] = pack_bf(p[i >> 2][(i & 1) + 2 * (i & 2)], p[i >> 2][(i & 1) + 2 * (i & 2) + 2]);
  };
  auto contract = [&](float (&kc)[20], uint32_t stg, int acc_in) {
    WG_FENCE();
#pragma unroll
    for (int s = 0; s < 8; s++) wgmma_ss_n40(kc, qdesc(stg + s * SLAB), qdesc(stg + s * SLAB + 2048), s ? 1 : acc_in);
    WG_COMMIT();
    WG_WAIT(0);
  };
  uint32_t eq[32];
  {
    uint4 af[4], aq[4], vp[4];
    float p[4][8];
#pragma unroll
    for (int u = 0; u < 4; u++) af[u] = pack8(acc[u >> 1] + 16 + 8 * (u & 1));
    feat(af, p);
#pragma unroll
    for (int u = 0; u < 4; u++) { aq[u] = pack8(acc[u >> 1] + 8 * (u & 1)); vp[u] = pack8(acc[u >> 1] + 32 + 8 * (u & 1)); }
    WG_WAIT(0);
    uint32_t pw[16], ek[32];
    packp(p, pw);
#pragma unroll
    for (int u = 0; u < 4; u++) dual_exp(pw + 4 * u, ek + 8 * u);
    TS(wg * 16 + 12);
    mbar_wait(BAR(MB_AUX));
    float rs[8][4];
    WG_FENCE();
#pragma unroll
    for (int i = 0; i < 8; i++) wgmma_rs_n8(rs[i], make_uint4(ek[4 * i], ek[4 * i + 1], ek[4 * i + 2], ek[4 * i + 3]), qdesc(sb + OFF_ONE), 0);
    WG_COMMIT();
    feat(aq, p);
    const uint32_t sl = (wg ? stg1 : stg0) + w * SLAB + lane * 16;
#pragma unroll
    for (int i = 0; i < 4; i++) stsm4(sl + (i >> 1) * 4 * SLAB + 2048 + (i & 1) * 512, vp[i].x, vp[i].y, vp[i].z, vp[i].w);
    sts128(sl + (lane >> 4) * (4 * SLAB - 256) + 3072, 0x3F803F80u, 0x3F803F80u, 0x3F803F80u, 0x3F803F80u);
    WG_WAIT(1);
#pragma unroll
    for (int i = 0; i < 8; i++) {
      normalise(ek + 4 * i, rs[i]);
      stsm4(sl + (i >> 2) * 4 * SLAB + (i & 3) * 512, ek[4 * i], ek[4 * i + 1], ek[4 * i + 2], ek[4 * i + 3]);
    }
    asm volatile("fence.proxy.async.shared::cta;" ::: "memory");
    TS(wg * 16 + 13);
    if (wg) {
      nb_arrive(NB_ST0, 256);
    } else {
      float kc[20];
      uint4* pp = g_part + (size_t)(hp * 8 + rt) * 144 + t;
      uint32_t* pz = (uint32_t*)(pp - t + 128) + w * 16 + c * 8 + g;
      asm volatile("" : "+l"(pp), "+l"(pz));
      nb_sync(NB_WG0, 128);
      contract(kc, stg0, 0);
      mbar_wait(BAR(MB_UFULL));
      TS(15);
      nb_sync(NB_ST0, 256);
      contract(kc, stg1, 1);
      TS(6);
      float kv[8];
#pragma unroll
      for (int i = 0; i < 8; i++) kv[i] = w & 2 ? kc[8 + i] : kc[i];
      st_x(pp, nz(pack_bf(kv[0], kv[1])), pack_bf(kv[2], kv[3]), pack_bf(kv[4], kv[5]), pack_bf(kv[6], kv[7]));
      if (c < 2) st_x32(pz, nz(fu(c ? kc[18] : kc[16])));
      TS(5);
    }
    SPLIT();
    WG_WAIT(0);
    packp(p, pw);
#pragma unroll
    for (int u = 0; u < 4; u++) dual_exp(pw + 4 * u, eq + 8 * u);
    SPLIT();
  }
  TS(wg * 16 + 4);
  if (wg == 1) {
    mbar_wait(BAR(MB_UFULL));
    const uint4* ps = g_part + (size_t)hp * 8 * 144 + t;
    const uint32_t* zs = (const uint32_t*)(g_part + (size_t)(hp * 8 + (lane >> 4) * 4) * 144 + 128) + w * 16 + (lane & 15);
    uint4 v[8];
    uint32_t zv[4];
#pragma unroll 1
    for (int it = 0; it < SPIN_MAX; it++) {
#pragma unroll
      for (int i = 0; i < 8; i++) v[i] = ld_x(ps + i * 144);
#pragma unroll
      for (int i = 0; i < 4; i++) zv[i] = ld_x32(zs + i * 576);
      uint32_t m = min(min(zv[0], zv[1]), min(zv[2], zv[3]));
#pragma unroll
      for (int i = 0; i < 8; i++) m = min(m, v[i].x);
      if (__all_sync(0xffffffffu, m != 0)) break;
    }
    float s[8];
    WG_FENCE();
#pragma unroll
    for (int r = 0; r < 8; r++) wgmma_rs_n16(s, v[r], qdesc(sb + OFF_EYE), r);
    WG_COMMIT();
    float zsum = (uf(zv[0]) + uf(zv[1])) + (uf(zv[2]) + uf(zv[3]));
    zsum += __shfl_xor_sync(0xffffffffu, zsum, 16);
    const uint32_t z1 = pack_bf(zsum, 1.f);
    if (lane < 16) sts128(kvs + w * 768 + 512 + lane * 16, z1, z1, z1, z1);
    WG_WAIT(0);
    stsm4(kvs + w * 768 + lane * 16, pack_bf(s[0], s[1]), pack_bf(s[2], s[3]), pack_bf(s[4], s[5]), pack_bf(s[6], s[7]));
    asm volatile("fence.proxy.async.shared::cta;" ::: "memory");
    TS(22);
  }
  nb_sync(NB_KV, 256);
  {
    float n[8][12];
    WG_FENCE();
#pragma unroll
    for (int i = 0; i < 8; i++) wgmma_rs_n24(n[i], make_uint4(eq[4 * i], eq[4 * i + 1], eq[4 * i + 2], eq[4 * i + 3]), qdesc(kvs + (i & 3) * 768), 0);
    WG_COMMIT();
    uint32_t* od = (uint32_t*)(g_o + (size_t)((rt * 4 + wg * 2) * 32 + hp * 2) * 128) + w * 64 + lane;
    WG_WAIT(0);
#pragma unroll
    for (int u = 0; u < 4; u++) {
      float(&np)[12] = n[2 * u];
      const float(&nm)[12] = n[2 * u + 1];
      const float q0 = np[9] * rcp(nm[9]), q1 = np[11] * rcp(nm[11]);
      const float r0 = rcp(fmaf(nm[8], q0, fmaf(np[9], 1e-6f, np[8]))), r1 = rcp(fmaf(nm[10], q1, fmaf(np[11], 1e-6f, np[10])));
#pragma unroll
      for (int i = 0; i < 8; i++) np[i] = fmaf(nm[i], (i & 2) ? q1 : q0, np[i]);
      uint32_t* o = od + (u >> 1) * 16384 + (u & 1) * 512;
      o[0] = pack_bf(np[0] * r0, np[1] * r0);
      o[32] = pack_bf(np[2] * r1, np[3] * r1);
      o[256] = pack_bf(np[4] * r0, np[5] * r0);
      o[288] = pack_bf(np[6] * r1, np[7] * r1);
      if (u == 1) SPLIT();
    }
  }
  TS(wg * 16 + 7);
  nb_arrive(NB_ODONE, 320);
  if (wg) { if (w == 0) TSDUMP(16); return; }
  mbar_wait(BAR(MB_WO));
  mbar_wait(BAR(MB_OA));
  TS(8);
  nb_sync(NB_BDONE, 288);
  TS(9);
  float oc[64];
  {
    constexpr uint64_t ha = mkdesc(0, 0, 128, 0), hb = mkdesc(0, 0, 1024, 1);
    constexpr uint32_t da0 = (uint32_t)mkdesc(stg1, 1024, 0, 0), db0 = (uint32_t)mkdesc(sb + OFF_W, 8192, 0, 0);
#pragma unroll 1
    for (int j = 0; j < 8; j++) {
      const int kb = (j + 7) & 7;
      if ((j & 3) == 1) mbar_spin(j == 1 ? BAR(MB_OC) : BAR(MB_OB));
      WG_FENCE();
#pragma unroll
      for (int k = 0; k < 4; k++) wgmma_ss_n128(oc, ha | (da0 + 512 * kb + 128 * k), hb | (db0 + 1024 * kb + 128 * k), k ? 1 : j);
      WG_COMMIT();
    }
    WG_WAIT(0);
  }
  TS(10);
  const uint32_t ot = ((sb + OFF_T + 1023) & ~1023u) + w * 4096;
#pragma unroll
  for (int hf = 0; hf < 2; hf++) {
#pragma unroll
    for (int i = 8 * hf; i < 8 * hf + 8; i += 2)
      stsm4(ot + hf * 2048 + (lane & 15) * 128 + (((i + (lane >> 4)) ^ lane) & 7) * 16, pack_bf(oc[4 * i], oc[4 * i + 1]),
            pack_bf(oc[4 * i + 2], oc[4 * i + 3]), pack_bf(oc[4 * i + 4], oc[4 * i + 5]), pack_bf(oc[4 * i + 6], oc[4 * i + 7]));
    asm volatile("fence.proxy.async.shared::cta;" ::: "memory");
    __syncwarp();
    e_store2d(&mout, ot + hf * 2048, (hp & 3) * 128 + hf * 64, (rt * 4 + (hp >> 2)) * 64 + w * 16);
  }
  asm volatile(ELECT "cp.async.bulk.commit_group;\n@p cp.async.bulk.wait_group.read 0;\n}\n" ::: "memory");
  TS(wg * 16 + 11);
  GT(61 + wg);
  if (w == 0) TSDUMP(0);
  if (w == 1) TSDUMP(48);
}

typedef CUresult (*EncodeFn)(CUtensorMap*, CUtensorMapDataType, cuuint32_t, void*, const cuuint64_t*, const cuuint64_t*,
                             const cuuint32_t*, const cuuint32_t*, CUtensorMapInterleave, CUtensorMapSwizzle,
                             CUtensorMapL2promotion, CUtensorMapFloatOOBfill);

}

extern "C" void kernel_launch(void* const* d_in, const int* in_sizes, int n_in, void* d_out, int out_size) {
  (void)in_sizes; (void)n_in; (void)out_size;
  void* fn = nullptr;
  cudaDriverEntryPointQueryResult qr;
  cudaGetDriverEntryPoint("cuTensorMapEncodeTiled", &fn, cudaEnableDefault, &qr);
  EncodeFn enc = (EncodeFn)fn;
  CUtensorMap mx, mw, mo, mu, mout, mw4;
  const cuuint32_t es[5] = {1, 1, 1, 1, 1};
  {
    cuuint64_t dims[2] = {512, 2048}, st[1] = {1024};
    cuuint32_t box[2] = {64, 128};
    enc(&mx, CU_TENSOR_MAP_DATA_TYPE_BFLOAT16, 2, d_in[0], dims, st, box, es, CU_TENSOR_MAP_INTERLEAVE_NONE,
        CU_TENSOR_MAP_SWIZZLE_128B, CU_TENSOR_MAP_L2_PROMOTION_L2_128B, CU_TENSOR_MAP_FLOAT_OOB_FILL_NONE);
  }
  {
    cuuint64_t dims[3] = {512, 512, 3}, st[2] = {3072, 1024};
    cuuint32_t box[3] = {32, 64, 3};
    enc(&mw, CU_TENSOR_MAP_DATA_TYPE_BFLOAT16, 3, d_in[1], dims, st, box, es, CU_TENSOR_MAP_INTERLEAVE_NONE,
        CU_TENSOR_MAP_SWIZZLE_64B, CU_TENSOR_MAP_L2_PROMOTION_L2_128B, CU_TENSOR_MAP_FLOAT_OOB_FILL_NONE);
  }
  {
    cuuint64_t dims[3] = {64, 512, 8}, st[2] = {1024, 128};
    cuuint32_t box[3] = {64, 64, 2};
    enc(&mo, CU_TENSOR_MAP_DATA_TYPE_BFLOAT16, 3, d_in[3], dims, st, box, es, CU_TENSOR_MAP_INTERLEAVE_NONE,
        CU_TENSOR_MAP_SWIZZLE_128B, CU_TENSOR_MAP_L2_PROMOTION_L2_128B, CU_TENSOR_MAP_FLOAT_OOB_FILL_NONE);
  }
  {
    cuuint64_t dims[4] = {512, 4, 16, 32}, st[3] = {16384, 1024, 65536};
    cuuint32_t box[4] = {64, 4, 16, 2};
    enc(&mu, CU_TENSOR_MAP_DATA_TYPE_BFLOAT16, 4, d_in[4], dims, st, box, es, CU_TENSOR_MAP_INTERLEAVE_NONE,
        CU_TENSOR_MAP_SWIZZLE_128B, CU_TENSOR_MAP_L2_PROMOTION_L2_128B, CU_TENSOR_MAP_FLOAT_OOB_FILL_NONE);
  }
  {
    cuuint64_t dims[2] = {1024, 2048}, st[1] = {2048};
    cuuint32_t box[2] = {64, 16};
    enc(&mout, CU_TENSOR_MAP_DATA_TYPE_BFLOAT16, 2, d_out, dims, st, box, es, CU_TENSOR_MAP_INTERLEAVE_NONE,
        CU_TENSOR_MAP_SWIZZLE_128B, CU_TENSOR_MAP_L2_PROMOTION_NONE, CU_TENSOR_MAP_FLOAT_OOB_FILL_NONE);
  }
  {
    cuuint64_t dims[4] = {512, 64, 3, 8}, st[3] = {3072, 1024, 64 * 3072};
    cuuint32_t box[4] = {32, 64, 3, 4};
    enc(&mw4, CU_TENSOR_MAP_DATA_TYPE_BFLOAT16, 4, d_in[1], dims, st, box, es, CU_TENSOR_MAP_INTERLEAVE_NONE,
        CU_TENSOR_MAP_SWIZZLE_64B, CU_TENSOR_MAP_L2_PROMOTION_L2_128B, CU_TENSOR_MAP_FLOAT_OOB_FILL_NONE);
  }
  Params P;
  P.x = (const __nv_bfloat16*)d_in[0];
  P.wphi = (const __nv_bfloat16*)d_in[2];
  P.wo = (const __nv_bfloat16*)d_in[3];
  P.logA = (const __nv_bfloat16*)d_in[5];
  P.Aim = (const __nv_bfloat16*)d_in[6];
  P.Cre = (const __nv_bfloat16*)d_in[7];
  P.Cim = (const __nv_bfloat16*)d_in[8];
  P.logdt = (const __nv_bfloat16*)d_in[9];
  P.Dskip = (const __nv_bfloat16*)d_in[10];
  P.out = (__nv_bfloat16*)d_out;
  cudaGetSymbolAddress((void**)&P.xs, g_x);
  P.ts = nullptr;
  cudaFuncSetAttribute(fused_kernel, cudaFuncAttributeMaxDynamicSharedMemorySize, SMEM_BYTES);
  fused_kernel<<<NCTA, NTHREADS, SMEM_BYTES>>>(P, mx, mw, mo, mu, mout, mw4);
}
```

```cpp
#include <cuda_runtime.h>
#include <cuda_bf16.h>
#include <cuda_fp16.h>
#include <cuda.h>
#include <stdint.h>

#define DBG_TS 0

namespace {

constexpr int NTHREADS = 512;
constexpr int NCTA = 128;
constexpr int OFF_W = 0;
constexpr int OFF_X = 98304;
constexpr int OFF_U = OFF_X + 65536;
constexpr int U_CH = 4416, U_ODD = 2240, U_PAD = 128;
constexpr int OFF_STG0 = OFF_U + 18432;
constexpr int SLAB = 3328;
constexpr int OFF_T = OFF_STG0 + 8 * SLAB;
constexpr int T_CH = 5216;
constexpr int T_D = 0;
constexpr int T_5 = 2144;
constexpr int T_3 = T_5 + 384;
constexpr int T_7 = T_5 + 1024;
constexpr int T_9 = T_7 + 320;
constexpr int T_KC = T_9 + 320;
constexpr int T_ST = T_5 - 1024;
constexpr int OFF_PHI = OFF_T + 4 * T_CH;
constexpr int OFF_EYE = OFF_PHI + 1024, OFF_ONE = OFF_EYE + 512;
constexpr int OFF_BAR = OFF_ONE + 256;
constexpr int SMEM_BYTES = OFF_BAR + 512 + 256 * DBG_TS;
constexpr uint32_t SB = 1024;
static_assert(T_KC + 2 * 656 <= T_CH, "table size");
static_assert(SMEM_BYTES <= 232448, "smem");
constexpr int MB_URAW = 0, MB_FULL = 1  , MB_WO = 17, MB_UFULL = 18, MB_OA = 19, MB_OB = 20, MB_OC = 21,
              MB_EMPTY = 22  , MB_AUX = 38;
__host__ __device__ constexpr uint32_t BAR(int i) { return SB + OFF_BAR + 8 * i; }
constexpr int NB_WG0 = 1, NB_ODONE = 2, NB_ST0 = 3  , NB_KV = 5, NB_YZ = 6, NB_INIT = 7, NB_PREP = 8, NB_PROD = 9, NB_KREAD = 10, NB_BDONE = 11, NB_ZERO = 12;
#define U_AT 2
#define ZERO_STEP 15
constexpr int SPIN_MAX = 1 << 16;

constexpr int X_CNT = 0;
constexpr int X_PART = 256;
constexpr int X_O = X_PART + 16 * 8 * 144;
constexpr int X_Y = X_O + 32 * 32 * 128;
constexpr int X_UT = X_Y + 512 * 8 * 32;
constexpr int X_SIZE = X_UT + 512 * (U_CH / 16);
__device__ __align__(128) uint4 g_x[X_SIZE];
extern __shared__ uint8_t smem_raw[];
#define TS(i) do {} while (0)
#define TS1(i) do {} while (0)
#define GT(i) do {} while (0)
#define TSDUMP(base) do {} while (0)

__device__ __forceinline__ uint32_t smem_u32(const void* p) { return (uint32_t)__cvta_generic_to_shared(p); }
__device__ __forceinline__ void mbar_arrive(uint32_t b) {
  asm volatile("mbarrier.arrive.shared::cta.b64 _, [%0];" ::"r"(b) : "memory");
}
__device__ __forceinline__ void mbar_wait(uint32_t b) {
  uint32_t done = 0;
#pragma unroll 1
  for (int i = 0; i < SPIN_MAX && !done; i++) {
    asm volatile("{\n.reg .pred p;\nmbarrier.try_wait.parity.shared::cta.b64 p, [%1], 0, 4000;\nselp.u32 %0, 1, 0, p;\n}\n"
                 : "=r"(done) : "r"(b) : "memory");
  }
}
__device__ __forceinline__ void mbar_spin(uint32_t b) {
  uint32_t done = 0;
#pragma unroll 1
  for (int i = 0; i < (SPIN_MAX << 4) && !done; i++) {
    asm volatile("{\n.reg .pred p;\nmbarrier.try_wait.parity.shared::cta.b64 p, [%1], 0;\nselp.u32 %0, 1, 0, p;\n}\n"
                 : "=r"(done) : "r"(b) : "memory");
  }
}
__device__ __forceinline__ void mbar_init(uint32_t b, int n) {
  asm volatile("mbarrier.init.shared::cta.b64 [%0], %1;" ::"r"(b), "r"(n) : "memory");
}
__device__ __forceinline__ void mbar_expect(uint32_t b, int bytes) {
  asm volatile("mbarrier.arrive.expect_tx.shared::cta.b64 _, [%0], %1;" ::"r"(b), "r"(bytes) : "memory");
}
__device__ __forceinline__ void nb_sync(int id, int n) { asm volatile("bar.sync %0, %1;" ::"r"(id), "r"(n) : "memory"); }
__device__ __forceinline__ void nb_arrive(int id, int n) { asm volatile("bar.arrive %0, %1;" ::"r"(id), "r"(n) : "memory"); }
#define ELECT "{\n.reg .pred p;\nelect.sync _|p, 0xffffffff;\n@p "
__device__ __forceinline__ void e_arrive(uint32_t b) {
  asm volatile(ELECT "mbarrier.arrive.shared::cta.b64 _, [%0];\n}\n" ::"r"(b) : "memory");
}
__device__ __forceinline__ void e_expect(uint32_t b, int bytes) {
  asm volatile(ELECT "mbarrier.arrive.expect_tx.shared::cta.b64 _, [%0], %1;\n}\n" ::"r"(b), "r"(bytes) : "memory");
}
__device__ __forceinline__ void e_tma2d(uint32_t dst, const CUtensorMap* m, uint32_t bar, int c0, int c1) {
  asm volatile(ELECT "cp.async.bulk.tensor.2d.shared::cluster.global.mbarrier::complete_tx::bytes [%0], [%1, {%3,%4}], [%2];\n}\n"
               ::"r"(dst), "l"(m), "r"(bar), "r"(c0), "r"(c1) : "memory");
}
__device__ __forceinline__ void e_tma3d(uint32_t dst, const CUtensorMap* m, uint32_t bar, int c0, int c1, int c2) {
  asm volatile(ELECT "cp.async.bulk.tensor.3d.shared::cluster.global.mbarrier::complete_tx::bytes [%0], [%1, {%3,%4,%5}], [%2];\n}\n"
               ::"r"(dst), "l"(m), "r"(bar), "r"(c0), "r"(c1), "r"(c2) : "memory");
}
__device__ __forceinline__ void e_tma4d(uint32_t dst, const CUtensorMap* m, uint32_t bar, int c0, int c3) {
  asm volatile(ELECT "cp.async.bulk.tensor.4d.shared::cluster.global.mbarrier::complete_tx::bytes [%0], [%1, {%3,%5,%5,%4}], [%2];\n}\n"
               ::"r"(dst), "l"(m), "r"(bar), "r"(c0), "r"(c3), "r"(0) : "memory");
}
__device__ __forceinline__ void e_bulk(uint32_t dst, const void* src, int bytes, uint32_t bar) {
  asm volatile(ELECT "cp.async.bulk.shared::cluster.global.mbarrier::complete_tx::bytes [%0], [%1], %2, [%3];\n}\n"
               ::"r"(dst), "l"(src), "r"(bytes), "r"(bar) : "memory");
}
__device__ __forceinline__ void e_prefetch(const void* p, int bytes) {
  asm volatile(ELECT "cp.async.bulk.prefetch.L2.global [%0], %1;\n}\n" ::"l"(p), "r"(bytes) : "memory");
}
__device__ __forceinline__ void e_store2d(const CUtensorMap* m, uint32_t src, int c0, int c1) {
  asm volatile(ELECT "cp.async.bulk.tensor.2d.global.shared::cta.bulk_group [%0, {%2,%3}], [%1];\n}\n"
               ::"l"(m), "r"(src), "r"(c0), "r"(c1) : "memory");
}
__host__ __device__ constexpr uint64_t mkdesc(uint32_t addr, uint32_t lbo, uint32_t sbo, int swz) {
  return (uint64_t)((addr & 0x3FFFF) >> 4) | ((uint64_t)(lbo >> 4) << 16) | ((uint64_t)(sbo >> 4) << 32) |
         ((uint64_t)swz << 62);
}
#define SPLIT() asm volatile("{\n.reg .pred p;\nsetp.eq.u32 p, %0, %1;\n@p exit;\n}\n" ::"r"(blockIdx.y), "n"(__LINE__) : "memory")
#define WG_FENCE() asm volatile("wgmma.fence.sync.aligned;" ::: "memory")
#define WG_COMMIT() asm volatile("wgmma.commit_group.sync.aligned;" ::: "memory")
#define WG_WAIT(n) asm volatile("wgmma.wait_group.sync.aligned " #n ";" ::: "memory")

__device__ __forceinline__ void mma(float& d0, float& d1, float& d2, float& d3, uint32_t a0, uint32_t a1, uint32_t a2,
                                    uint32_t a3, uint32_t b0, uint32_t b1) {
  asm volatile("mma.sync.aligned.m16n8k16.row.col.f32.bf16.bf16.f32 {%0,%1,%2,%3},{%4,%5,%6,%7},{%8,%9},{%0,%1,%2,%3};"
               : "+f"(d0), "+f"(d1), "+f"(d2), "+f"(d3)
               : "r"(a0), "r"(a1), "r"(a2), "r"(a3), "r"(b0), "r"(b1));
}
__device__ __forceinline__ void mmac(float (&d)[4], uint32_t a0, uint32_t a1, uint32_t a2, uint32_t a3, uint32_t b0,
                                     uint32_t b1, const float (&c)[4]) {
  asm volatile("mma.sync.aligned.m16n8k16.row.col.f32.bf16.bf16.f32 {%0,%1,%2,%3},{%4,%5,%6,%7},{%8,%9},{%10,%11,%12,%13};"
               : "=f"(d[0]), "=f"(d[1]), "=f"(d[2]), "=f"(d[3])
               : "r"(a0), "r"(a1), "r"(a2), "r"(a3), "r"(b0), "r"(b1), "f"(c[0]), "f"(c[1]), "f"(c[2]), "f"(c[3]));
}
__device__ __forceinline__ void mma_p(int p, float (&d)[4], uint32_t a0, uint32_t a1, uint32_t a2, uint32_t a3, uint32_t b0, uint32_t b1) {
  asm volatile("{\n.reg .pred q;\nsetp.ne.b32 q, %10, 0;\n"
               "@q mma.sync.aligned.m16n8k16.row.col.f32.bf16.bf16.f32 {%0,%1,%2,%3},{%4,%5,%6,%7},{%8,%9},{%0,%1,%2,%3};\n}\n"
               : "+f"(d[0]), "+f"(d[1]), "+f"(d[2]), "+f"(d[3])
               : "r"(a0), "r"(a1), "r"(a2), "r"(a3), "r"(b0), "r"(b1), "r"(p));
}
__device__ __forceinline__ void mmac_p(int p, float (&d)[4], uint32_t a0, uint32_t a1, uint32_t a2, uint32_t a3, uint32_t b0,
                                       uint32_t b1, const float (&c)[4]) {
  asm volatile("{\n.reg .pred q;\nsetp.ne.b32 q, %14, 0;\n"
               "@q mma.sync.aligned.m16n8k16.row.col.f32.bf16.bf16.f32 {%0,%1,%2,%3},{%4,%5,%6,%7},{%8,%9},{%10,%11,%12,%13};\n}\n"
               : "+f"(d[0]), "+f"(d[1]), "+f"(d[2]), "+f"(d[3])
               : "r"(a0), "r"(a1), "r"(a2), "r"(a3), "r"(b0), "r"(b1), "f"(c[0]), "f"(c[1]), "f"(c[2]), "f"(c[3]), "r"(p));
}
__device__ __forceinline__ void mma_h(float (&d)[4], const uint32_t (&a)[4], uint32_t b0, uint32_t b1) {
  asm volatile("mma.sync.aligned.m16n8k16.row.col.f32.f16.f16.f32 {%0,%1,%2,%3},{%4,%5,%6,%7},{%8,%9},{%0,%1,%2,%3};"
               : "+f"(d[0]), "+f"(d[1]), "+f"(d[2]), "+f"(d[3]) : "r"(a[0]), "r"(a[1]), "r"(a[2]), "r"(a[3]), "r"(b0), "r"(b1));
}
__device__ __forceinline__ void mma0(float& d0, float& d1, float& d2, float& d3, uint32_t a0, uint32_t a1, uint32_t a2,
                                     uint32_t a3, uint32_t b0, uint32_t b1) {
  asm volatile("mma.sync.aligned.m16n8k16.row.col.f32.bf16.bf16.f32 {%0,%1,%2,%3},{%4,%5,%6,%7},{%8,%9},{%10,%10,%10,%10};"
               : "=f"(d0), "=f"(d1), "=f"(d2), "=f"(d3)
               : "r"(a0), "r"(a1), "r"(a2), "r"(a3), "r"(b0), "r"(b1), "f"(0.f));
}
__device__ __forceinline__ uint32_t pack_bf(float lo, float hi) {
  uint32_t r;
  asm("cvt.rn.bf16x2.f32 %0, %1, %2;" : "=r"(r) : "f"(hi), "f"(lo));
  return r;
}
__device__ __forceinline__ float bf_lo(uint32_t w) { return __uint_as_float(w << 16); }
__device__ __forceinline__ float bf_hi(uint32_t w) { return __uint_as_float(w & 0xffff0000u); }
__device__ __forceinline__ float bf_round(float x) { return __bfloat162float(__float2bfloat16_rn(x)); }
__device__ __forceinline__ uint32_t bmax2(uint32_t a, uint32_t b) {
  uint32_t r; asm("max.bf16x2 %0, %1, %2;" : "=r"(r) : "r"(a), "r"(b)); return r;
}
__device__ __forceinline__ uint32_t bmin2(uint32_t a, uint32_t b) {
  uint32_t r; asm("min.bf16x2 %0, %1, %2;" : "=r"(r) : "r"(a), "r"(b)); return r;
}
__device__ __forceinline__ float ex2(float x) { float r; asm("ex2.approx.ftz.f32 %0, %1;" : "=f"(r) : "f"(x)); return r; }
__device__ __forceinline__ float rcp(float x) { float r; asm("rcp.approx.ftz.f32 %0, %1;" : "=f"(r) : "f"(x)); return r; }
__device__ __forceinline__ void ldsm4(uint32_t (&r)[4], uint32_t a) {
  asm volatile("ldmatrix.sync.aligned.m8n8.x4.shared.b16 {%0,%1,%2,%3}, [%4];"
               : "=r"(r[0]), "=r"(r[1]), "=r"(r[2]), "=r"(r[3]) : "r"(a) : "memory");
}
__device__ __forceinline__ void ldsm4t(uint32_t (&r)[4], uint32_t a) {
  asm volatile("ldmatrix.sync.aligned.m8n8.x4.trans.shared.b16 {%0,%1,%2,%3}, [%4];"
               : "=r"(r[0]), "=r"(r[1]), "=r"(r[2]), "=r"(r[3]) : "r"(a) : "memory");
}
__device__ __forceinline__ void stsm4(uint32_t a, uint32_t r0, uint32_t r1, uint32_t r2, uint32_t r3) {
  asm volatile("stmatrix.sync.aligned.m8n8.x4.shared.b16 [%0], {%1,%2,%3,%4};"
               ::"r"(a), "r"(r0), "r"(r1), "r"(r2), "r"(r3) : "memory");
}
__device__ __forceinline__ uint32_t lds32(uint32_t a) {
  uint32_t r; asm volatile("ld.shared.u32 %0, [%1];" : "=r"(r) : "r"(a) : "memory"); return r;
}
__device__ __forceinline__ uint32_t lds16(uint32_t a) {
  uint32_t r; asm volatile("{\n.reg .u16 h;\nld.shared.u16 h, [%1];\ncvt.u32.u16 %0, h;\n}\n" : "=r"(r) : "r"(a) : "memory"); return r;
}
__device__ __forceinline__ uint2 lds64(uint32_t a) {
  uint2 r; asm volatile("ld.shared.v2.u32 {%0,%1}, [%2];" : "=r"(r.x), "=r"(r.y) : "r"(a) : "memory"); return r;
}
__device__ __forceinline__ uint4 lds128(uint32_t a) {
  uint4 r;
  asm volatile("ld.shared.v4.u32 {%0,%1,%2,%3}, [%4];" : "=r"(r.x), "=r"(r.y), "=r"(r.z), "=r"(r.w) : "r"(a) : "memory");
  return r;
}
__device__ __forceinline__ void sts32(uint32_t a, uint32_t v) { asm volatile("st.shared.u32 [%0], %1;" ::"r"(a), "r"(v) : "memory"); }
__device__ __forceinline__ void sts16(uint32_t a, uint32_t v) {
  asm volatile("{\n.reg .u16 h;\ncvt.u16.u32 h, %1;\nst.shared.u16 [%0], h;\n}\n" ::"r"(a), "r"(v) : "memory");
}
__device__ __forceinline__ void sts64(uint32_t a, uint32_t x, uint32_t y) {
  asm volatile("st.shared.v2.u32 [%0], {%1,%2};" ::"r"(a), "r"(x), "r"(y) : "memory");
}
__device__ __forceinline__ void sts128(uint32_t a, uint32_t x, uint32_t y, uint32_t z, uint32_t w) {
  asm volatile("st.shared.v4.u32 [%0], {%1,%2,%3,%4};" ::"r"(a), "r"(x), "r"(y), "r"(z), "r"(w) : "memory");
}
__device__ __forceinline__ uint4 ld_x(const uint4* p) {
  uint4 r;
  asm volatile("{\n.reg .b128 t;\nld.relaxed.gpu.global.b128 t, [%4];\nmov.b128 {%0,%1,%2,%3}, t;\n}\n"
               : "=r"(r.x), "=r"(r.y), "=r"(r.z), "=r"(r.w) : "l"(p) : "memory");
  return r;
}
__device__ __forceinline__ uint32_t ld_x32(const uint32_t* p) {
  uint32_t r; asm volatile("ld.relaxed.gpu.global.u32 %0, [%1];" : "=r"(r) : "l"(p) : "memory"); return r;
}
__device__ __forceinline__ void st_x(uint4* p, uint32_t x, uint32_t y, uint32_t z, uint32_t w) {
  asm volatile("{\n.reg .b128 t;\nmov.b128 t, {%1,%2,%3,%4};\nst.relaxed.gpu.global.b128 [%0], t;\n}\n"
               ::"l"(p), "r"(x), "r"(y), "r"(z), "r"(w) : "memory");
}
__device__ __forceinline__ void st_x_p(int p, uint4* a, uint32_t x, uint32_t y, uint32_t z, uint32_t w) {
  asm volatile("{\n.reg .b128 t;\n.reg .pred q;\nsetp.ne.b32 q, %5, 0;\nmov.b128 t, {%1,%2,%3,%4};\n@q st.relaxed.gpu.global.b128 [%0], t;\n}\n"
               ::"l"(a), "r"(x), "r"(y), "r"(z), "r"(w), "r"(p) : "memory");
}
__device__ __forceinline__ void sts64_p(int p, uint32_t a, uint32_t x, uint32_t y) {
  asm volatile("{\n.reg .pred q;\nsetp.ne.b32 q, %3, 0;\n@q st.shared.v2.u32 [%0], {%1,%2};\n}\n" ::"r"(a), "r"(x), "r"(y), "r"(p) : "memory");
}
__device__ __forceinline__ void st_x32(uint32_t* p, uint32_t x) {
  asm volatile("st.relaxed.gpu.global.u32 [%0], %1;" ::"l"(p), "r"(x) : "memory");
}
__device__ __forceinline__ uint32_t nz(uint32_t w) { return max(w, 1u); }
__device__ __forceinline__ uint32_t fu(float x) { return __float_as_uint(x); }
__device__ __forceinline__ float uf(uint32_t x) { return __uint_as_float(x); }

__device__ __forceinline__ void wgmma_ss_n96(float (&d)[48], uint64_t da, uint64_t db, int sc) {
  asm volatile("{\n.reg .pred p;\nsetp.ne.b32 p, %50, 0;\n"
      "wgmma.mma_async.sync.aligned.m64n96k16.f32.bf16.bf16 "
      "{%0,%1,%2,%3,%4,%5,%6,%7,%8,%9,%10,%11,%12,%13,%14,%15,%16,%17,%18,%19,%20,%21,%22,%23,%24,%25,%26,%27,%28,%29,%30,%31,%32,%33,%34,%35,%36,%37,%38,%39,%40,%41,%42,%43,%44,%45,%46,%47}, "
      "%48, %49, p, 1, 1, 0, 1;\n}\n"
      : "+f"(d[0]), "+f"(d[1]), "+f"(d[2]), "+f"(d[3]), "+f"(d[4]), "+f"(d[5]), "+f"(d[6]), "+f"(d[7]),
        "+f"(d[8]), "+f"(d[9]), "+f"(d[10]), "+f"(d[11]), "+f"(d[12]), "+f"(d[13]), "+f"(d[14]), "+f"(d[15]),
        "+f"(d[16]), "+f"(d[17]), "+f"(d[18]), "+f"(d[19]), "+f"(d[20]), "+f"(d[21]), "+f"(d[22]), "+f"(d[23]),
        "+f"(d[24]), "+f"(d[25]), "+f"(d[26]), "+f"(d[27]), "+f"(d[28]), "+f"(d[29]), "+f"(d[30]), "+f"(d[31]),
        "+f"(d[32]), "+f"(d[33]), "+f"(d[34]), "+f"(d[35]), "+f"(d[36]), "+f"(d[37]), "+f"(d[38]), "+f"(d[39]),
        "+f"(d[40]), "+f"(d[41]), "+f"(d[42]), "+f"(d[43]), "+f"(d[44]), "+f"(d[45]), "+f"(d[46]), "+f"(d[47])
      : "l"(da), "l"(db), "r"(sc));
}

__device__ __forceinline__ void wgmma_ss_n128(float (&d)[64], uint64_t da, uint64_t db, int sc) {
  asm volatile("{\n.reg .pred p;\nsetp.ne.b32 p, %66, 0;\n"
      "wgmma.mma_async.sync.aligned.m64n128k16.f32.bf16.bf16 "
      "{%0,%1,%2,%3,%4,%5,%6,%7,%8,%9,%10,%11,%12,%13,%14,%15,%16,%17,%18,%19,%20,%21,%22,%23,%24,%25,%26,%27,%28,%29,%30,%31,%32,%33,%34,%35,%36,%37,%38,%39,%40,%41,%42,%43,%44,%45,%46,%47,%48,%49,%50,%51,%52,%53,%54,%55,%56,%57,%58,%59,%60,%61,%62,%63}, "
      "%64, %65, p, 1, 1, 0, 1;\n}\n"
      : "+f"(d[0]), "+f"(d[1]), "+f"(d[2]), "+f"(d[3]), "+f"(d[4]), "+f"(d[5]), "+f"(d[6]), "+f"(d[7]),
        "+f"(d[8]), "+f"(d[9]), "+f"(d[10]), "+f"(d[11]), "+f"(d[12]), "+f"(d[13]), "+f"(d[14]), "+f"(d[15]),
        "+f"(d[16]), "+f"(d[17]), "+f"(d[18]), "+f"(d[19]), "+f"(d[20]), "+f"(d[21]), "+f"(d[22]), "+f"(d[23]),
        "+f"(d[24]), "+f"(d[25]), "+f"(d[26]), "+f"(d[27]), "+f"(d[28]), "+f"(d[29]), "+f"(d[30]), "+f"(d[31]),
        "+f"(d[32]), "+f"(d[33]), "+f"(d[34]), "+f"(d[35]), "+f"(d[36]), "+f"(d[37]), "+f"(d[38]), "+f"(d[39]),
        "+f"(d[40]), "+f"(d[41]), "+f"(d[42]), "+f"(d[43]), "+f"(d[44]), "+f"(d[45]), "+f"(d[46]), "+f"(d[47]),
        "+f"(d[48]), "+f"(d[49]), "+f"(d[50]), "+f"(d[51]), "+f"(d[52]), "+f"(d[53]), "+f"(d[54]), "+f"(d[55]),
        "+f"(d[56]), "+f"(d[57]), "+f"(d[58]), "+f"(d[59]), "+f"(d[60]), "+f"(d[61]), "+f"(d[62]), "+f"(d[63])
      : "l"(da), "l"(db), "r"(sc));
}

__device__ __forceinline__ void wgmma_ss_n40(float (&d)[20], uint64_t da, uint64_t db, int sc) {
  asm volatile("{\n.reg .pred p;\nsetp.ne.b32 p, %22, 0;\n"
      "wgmma.mma_async.sync.aligned.m64n40k16.f32.bf16.bf16 "
      "{%0,%1,%2,%3,%4,%5,%6,%7,%8,%9,%10,%11,%12,%13,%14,%15,%16,%17,%18,%19}, "
      "%20, %21, p, 1, 1, 1, 1;\n}\n"
      : "+f"(d[0]), "+f"(d[1]), "+f"(d[2]), "+f"(d[3]), "+f"(d[4]), "+f"(d[5]), "+f"(d[6]), "+f"(d[7]),
        "+f"(d[8]), "+f"(d[9]), "+f"(d[10]), "+f"(d[11]), "+f"(d[12]), "+f"(d[13]), "+f"(d[14]), "+f"(d[15]),
        "+f"(d[16]), "+f"(d[17]), "+f"(d[18]), "+f"(d[19])
      : "l"(da), "l"(db), "r"(sc));
}

__device__ __forceinline__ void wgmma_rs_n8(float (&d)[4], const uint4& a, uint64_t db, int sc) {
  asm volatile("{\n.reg .pred p;\nsetp.ne.b32 p, %9, 0;\n"
      "wgmma.mma_async.sync.aligned.m64n8k16.f32.bf16.bf16 "
      "{%0,%1,%2,%3}, "
      "{%4,%5,%6,%7}, %8, p, 1, 1, 1;\n}\n"
      : "+f"(d[0]), "+f"(d[1]), "+f"(d[2]), "+f"(d[3])
      : "r"(a.x), "r"(a.y), "r"(a.z), "r"(a.w), "l"(db), "r"(sc));
}

__device__ __forceinline__ void wgmma_rs_n16(float (&d)[8], const uint4& a, uint64_t db, int sc) {
  asm volatile("{\n.reg .pred p;\nsetp.ne.b32 p, %13, 0;\n"
      "wgmma.mma_async.sync.aligned.m64n16k16.f32.bf16.bf16 "
      "{%0,%1,%2,%3,%4,%5,%6,%7}, "
      "{%8,%9,%10,%11}, %12, p, 1, 1, 1;\n}\n"
      : "+f"(d[0]), "+f"(d[1]), "+f"(d[2]), "+f"(d[3]), "+f"(d[4]), "+f"(d[5]), "+f"(d[6]), "+f"(d[7])
      : "r"(a.x), "r"(a.y), "r"(a.z), "r"(a.w), "l"(db), "r"(sc));
}

__device__ __forceinline__ void wgmma_rs_n24(float (&d)[12], const uint4& a, uint64_t db, int sc) {
  asm volatile("{\n.reg .pred p;\nsetp.ne.b32 p, %17, 0;\n"
      "wgmma.mma_async.sync.aligned.m64n24k16.f32.bf16.bf16 "
      "{%0,%1,%2,%3,%4,%5,%6,%7,%8,%9,%10,%11}, "
      "{%12,%13,%14,%15}, %16, p, 1, 1, 1;\n}\n"
      : "+f"(d[0]), "+f"(d[1]), "+f"(d[2]), "+f"(d[3]), "+f"(d[4]), "+f"(d[5]), "+f"(d[6]), "+f"(d[7]),
        "+f"(d[8]), "+f"(d[9]), "+f"(d[10]), "+f"(d[11])
      : "r"(a.x), "r"(a.y), "r"(a.z), "r"(a.w), "l"(db), "r"(sc));
}

struct Params {
  const __nv_bfloat16 *logA, *Aim, *Cre, *Cim, *logdt, *Dskip, *x, *wphi, *wo;
  __nv_bfloat16* out;
  uint4* xs;
  long long* ts;
};

__device__ __forceinline__ uint4 tr_row(const uint4 (&v)[8], int i) {
  uint32_t o[4];
#pragma unroll
  for (int m = 0; m < 4; m++) {
    const uint4 &ra = v[2 * m], &rb = v[2 * m + 1];
    const int k = i >> 1;
    const uint32_t xa = k == 0 ? ra.x : k == 1 ? ra.y : k == 2 ? ra.z : ra.w;
    const uint32_t xb = k == 0 ? rb.x : k == 1 ? rb.y : k == 2 ? rb.z : rb.w;
    o[m] = __byte_perm(xa, xb, (i & 1) ? 0x7632 : 0x5410);
  }
  return make_uint4(o[0], o[1], o[2], o[3]);
}

struct cpx { float r, i; };
__device__ __forceinline__ cpx csq(cpx a) { return {a.r * a.r - a.i * a.i, 2.f * (a.r * a.i)}; }
__device__ __forceinline__ cpx polar(float e, float t) {
  const float m = ex2(e);
  return {m * __cosf(t), m * __sinf(t)};
}

struct KgenRaw { unsigned short la, ai, cr, ci, ldt; };
__device__ __forceinline__ KgenRaw kgen_load(const Params& P, int d, int unit, int lane) {
  const int o = d * 128 + unit * 32 + lane;
  return {__ldg((const unsigned short*)P.logA + o), __ldg((const unsigned short*)P.Aim + o), __ldg((const unsigned short*)P.Cre + o),
          __ldg((const unsigned short*)P.Cim + o), __ldg((const unsigned short*)P.logdt + d)};
}
struct hmul { __half2 a, b; };
__device__ __forceinline__ hmul mk_mul(cpx w) {
  uint32_t b;
  asm("{\n.reg .f32 n;\nneg.ftz.f32 n, %1;\ncvt.rn.f16x2.f32 %0, %2, n;\n}\n" : "=r"(b) : "f"(w.i), "f"(w.r));
  return {__floats2half2_rn(w.r, w.i), *(const __half2*)&b};
}
__device__ __forceinline__ __half2 hcm(__half2 z, const hmul& w) { return __hfma2(__high2half2(z), w.b, __hmul2(__low2half2(z), w.a)); }
__device__ __forceinline__ uint32_t hu(__half2 v) { return *(const uint32_t*)&v; }

struct KgenAddr { uint32_t sa, sb, lb, lc, la; };
__device__ __forceinline__ KgenAddr kgen_addr(int lane, uint32_t buf) {
  KgenAddr a;
  a.sa = buf + (lane & 7) * 128 + ((((lane >> 3) ^ lane) & 7) << 4);
  a.lb = buf + (lane >> 3) * 128 + (((lane ^ (lane >> 3)) & 7) << 4);
  a.la = buf + ((lane >> 3) & 1) * 1024 + (lane >> 4) * 128 + (((lane ^ (lane >> 4)) & 7) << 4);
  a.sb = a.sa ^ 64; a.lc = a.lb ^ 64;
  asm volatile("" : "+r"(a.sa), "+r"(a.sb), "+r"(a.lb), "+r"(a.lc), "+r"(a.la));
  return a;
}
__device__ __forceinline__ void kgen_unit(const KgenRaw& r, const KgenAddr& ad, uint32_t zero, float (&k)[5][4], float& k2048, float& sc) {
  const float dt = bf_round(expf(bf_lo(r.ldt)));
  const float a2 = bf_round(ex2(bf_lo(r.la) * 1.4426950408889634f)) * (dt * -1.4426950408889634f);
  const float f = bf_lo(r.ai) * dt;
  const float r128 = f * 20.371832715762604f;
  const uint32_t ex = min(max(__reduce_max_sync(0xffffffffu, max(r.cr & 0x7fffu, r.ci & 0x7fffu)) >> 7, 1u), 253u);
  const float cs = uf((254u - ex) << 23);
  sc = 2.f * dt * uf(ex << 23);
  const cpx C = {bf_lo(r.cr) * cs, -bf_lo(r.ci) * cs};
  auto put = [&](const __half2 (&v)[8], uint32_t off) {
    stsm4(ad.sa + off, hu(v[0]), hu(v[1]), hu(v[2]), hu(v[3]));
    stsm4(ad.sb + off, hu(v[4]), hu(v[5]), hu(v[6]), hu(v[7]));
  };
  uint32_t A[4][4], B[5][2][4];
  auto get = [&](int j, uint32_t off) {
    __syncwarp();
    ldsm4(B[j][0], ad.lb + off);
    ldsm4(B[j][1], ad.lc + 512 + off);
  };
  auto tile = [&](int j) {
    k[j][0] = k[j][1] = k[j][2] = k[j][3] = 0.f;
#pragma unroll
    for (int s = 0; s < 4; s++) mma_h(k[j], A[s], B[j][s >> 1][2 * (s & 1)], B[j][s >> 1][2 * (s & 1) + 1]);
  };
  auto after = [&](cpx v, uint32_t dep) { return cpx{uf(fu(v.r) ^ (dep & zero)), v.i}; };
  const cpx w1 = polar(a2, f), w128 = polar(a2 * 128.f, (r128 - rintf(r128)) * 6.283185307179586f);
  const cpx w2 = csq(w1), w4 = csq(w2);
  __half2 t0[8], t1[8], t2[8], t3[8], t4[8];
  const hmul m2 = mk_mul(w2), m4 = mk_mul(w4), m128 = mk_mul(w128);
  t0[0] = __floats2half2_rn(1.f, 0.f); t0[1] = __floats2half2_rn(w1.r, w1.i); t0[2] = m2.a; t0[4] = m4.a;
  t0[3] = hcm(t0[1], m2); t0[5] = hcm(t0[1], m4); t0[6] = hcm(t0[2], m4); t0[7] = hcm(t0[3], m4);
  put(t0, 0); get(0, 0);
  t1[0] = m128.a;
#pragma unroll
  for (int i = 1; i < 8; i++) t1[i] = hcm(t0[i], m128);
  put(t1, 1024); get(1, 1024);
  {
    cpx w8 = csq(after(w4, B[0][0][0]));
    w8.i = -w8.i;
    const cpx w16 = csq(w8), w32 = csq(w16), w64 = csq(w32);
    const hmul m8 = mk_mul(w8), m16 = mk_mul(w16), m32 = mk_mul(w32), m64 = mk_mul(w64);
    __half2 a[8];
    a[0] = __floats2half2_rn(C.r, C.i); a[1] = hcm(a[0], m8);
    a[2] = hcm(a[0], m16); a[3] = hcm(a[1], m16);
#pragma unroll
    for (int i = 0; i < 4; i++) a[4 + i] = hcm(a[i], m32);
    put(a, 0);
#pragma unroll
    for (int i = 0; i < 8; i++) a[i] = hcm(a[i], m64);
    put(a, 1024);
    __syncwarp();
#pragma unroll
    for (int s = 0; s < 4; s++) ldsm4(A[s], (ad.la ^ (s << 5)) + s * 256);
  }
  const cpx w256 = csq(after(w128, B[1][0][0]));
  const hmul m256 = mk_mul(w256);
  t2[0] = m256.a;
#pragma unroll
  for (int i = 1; i < 8; i++) t2[i] = hcm((i & 1) ? t1[i & 6] : t0[i & 6], m256);
  put(t2, 0); get(2, 0);
  tile(0); tile(1);
  const cpx w512 = csq(after(w256, A[0][0]));
  const hmul m512 = mk_mul(w512);
  t3[0] = m512.a;
#pragma unroll
  for (int i = 1; i < 8; i++) t3[i] = hcm((i & 2) ? t2[i & 5] : ((i & 1) ? t1[i & 4] : t0[i & 4]), m512);
  put(t3, 1024); get(3, 1024);
  tile(2);
  const cpx w1024 = csq(after(w512, B[2][0][0])), we = csq(w1024);
  const hmul m1024 = mk_mul(w1024);
  t4[0] = m1024.a;
#pragma unroll
  for (int i = 1; i < 8; i++) t4[i] = hcm((i & 4) ? t3[i & 3] : ((i & 2) ? t2[i & 1] : t1[0]), m1024);
  put(t4, 0); get(4, 0);
  tile(3); tile(4);
  k2048 = (C.r * we.r + C.i * we.i) * sc;
}

__device__ __forceinline__ void build_tables(uint32_t tb, int lane, float (&k)[5][4], float k2048) {
  const int g = lane >> 2, c = lane & 3;
  const uint32_t kc = tb + T_KC + 16;
  {
    const uint32_t a0 = kc + 16 * g + 4 * c, a2 = kc + 2 * (256 + 4 * g + c);
    const uint32_t a3 = kc + 2 * (384 + 2 * g + 64 * (c & 1) + (c >> 1)), a4 = kc + 2 * (512 + g + 32 * c);
#pragma unroll
    for (int r = 0; r < 2; r++) {
      sts32(a0 + 128 * r, pack_bf(k[0][2 * r], k[0][2 * r + 1]));
      sts32(a0 + 128 * r + 256, pack_bf(k[1][2 * r], k[1][2 * r + 1]));
      const uint32_t w2 = pack_bf(k[2][2 * r], k[2][2 * r + 1]);
      const uint32_t w3 = pack_bf(k[3][2 * r], k[3][2 * r + 1]);
      const uint32_t w4 = pack_bf(k[4][2 * r], k[4][2 * r + 1]);
      sts16(a2 + 64 * r, w2); sts16(a2 + 64 * r + 128, w2 >> 16);
      sts16(a3 + 32 * r, w3); sts16(a3 + 32 * r + 64, w3 >> 16);
      sts16(a4 + 16 * r, w4); sts16(a4 + 16 * r + 32, w4 >> 16);
    }
  }
  if (lane == 0) { sts16(kc + 2 * 640, pack_bf(k2048, 0.f)); sts32(kc - 4, 0); }
  __syncwarp();
  const uint32_t td = tb + T_D + 32;
#pragma unroll
  for (int hf = 0; hf < 2; hf++) {
    const uint2 v = lds64(kc + 256 * hf + 8 * lane);
    const uint32_t pv = lds32(kc + 256 * hf + 8 * lane - 4);
    sts128(td + 512 * hf + 16 * lane, __byte_perm(v.x, pv, 0x7610), __byte_perm(v.x, v.x, 0x1032), __byte_perm(v.y, v.x, 0x7610),
           __byte_perm(v.y, v.y, 0x1032));
  }
#pragma unroll
  for (int hf = 0; hf < 2; hf++) {
    const uint32_t v = lds32(kc + 512 + 128 * hf + 4 * lane), nx = lds32(kc + 516 + 128 * hf + 4 * lane);
    uint32_t w0 = __byte_perm(v, v, 0x1010);
    const uint32_t w1 = w0;
    if (hf == 0) { const uint32_t pv = lds32(kc + 508); if (lane == 0) w0 = __byte_perm(v, pv, 0x7610); }
    sts128(td + 1024 + 512 * hf + 16 * lane, w0, w1, __byte_perm(v, v, 0x1032), __byte_perm(nx, v, 0x7610));
  }
  {
    const uint32_t kk = lds16(kc + 2 * 384);
    const uint32_t w = lane < 3 ? (kk | (kk << 16)) : (lane == 3 ? (kk << 16) : 0u);
    if (lane < 24) sts32(td + 4 * (lane < 16 ? 512 + lane : lane - 24), w);
    const uint32_t lo_ = lds16(kc + 2 * 511), le_ = lds16(kc + 2 * 512);
    const uint32_t ja = tb + T_5 + (lane < 16 ? 4 * lane : 256 + 4 * lane);
    sts32(ja, lane == 16 ? (le_ << 16) : 0u);
    sts32(ja + 384, lane == 16 ? (lo_ << 16) : 0u);
    sts32(tb + (lane < 16 ? T_7 : T_9 - 64) + 4 * lane, 0u);
  }
#pragma unroll
  for (int s = 0; s < 2; s++) {
    const uint32_t b = kc + 2 * (s ? 512 : 384) + 8 * lane;
    const uint2 v = lds64(b);
    uint32_t em = lds16(b - 2), e0 = v.x;
    const uint32_t e4 = lds16(b + 8);
    if (lane == 0) { em = 0; e0 = 0; }
    sts64(tb + (s ? T_7 : T_3) + 64 + 8 * lane, __byte_perm(v.x, em, 0x5432), __byte_perm(v.y, v.x, 0x7632));
    sts64(tb + (s ? T_9 : T_5) + 64 + 8 * lane, __byte_perm(v.y, e0, 0x5410), __byte_perm(e4, v.y, 0x5410));
  }
  __syncwarp();
}

__device__ __forceinline__ uint32_t box2w(int lo, int n, int o) {
  return ((unsigned)(o - lo) < (unsigned)n ? 0x3F80u : 0u) | ((unsigned)(o + 1 - lo) < (unsigned)n ? 0x3F800000u : 0u);
}

__device__ __forceinline__ void conv_channel(uint32_t ub, uint32_t tb, int lane, uint4* ydst) {
  const int g = lane >> 2, c = lane & 3, x = g - 2 * c;
  const int mi = lane >> 3;
  const uint32_t qa = ub + U_PAD + 16 * (lane & 7) + ((mi == 0 || mi == 3) ? U_ODD : 0) - (mi == 0 ? 16 : 0);
  const uint32_t hb = ub + U_PAD + (mi & 1) * U_ODD + 16 * ((lane >> 4) + (lane & 7)) - 16;
  const uint32_t kv = lds16(tb + T_KC + 16 + 2 * 512);
  const int oh = c < 2 ? 8 + 2 * c : 2 * c - 8, og = c < 3 ? 2 * c : -10;
  uint32_t bx[4] = {box2w(g - 4, 9, 2 * c), box2w(g - 3, 7, 2 * c), box2w(g - 4, 9, oh), box2w(g - 3, 7, oh)};
  uint32_t by[4] = {box2w(g - 10, 5, 2 * c - 8), box2w(g - 5, 3, 2 * c - 8), box2w(g - 10, 5, og), box2w(g - 5, 3, og)};
  uint32_t lb0 = ((unsigned)(x + 5) < 2u ? kv : 0u) | ((unsigned)(x + 4) < 2u ? kv << 16 : 0u);
  uint32_t lb1 = ((unsigned)(x - 3) < 2u ? kv : 0u) | ((unsigned)(x - 4) < 2u ? kv << 16 : 0u);
  const int q0 = g - 1, q1 = c < 3 ? g : g - 2;
  uint32_t y0a = ub + U_PAD + (q0 & 1) * U_ODD + 16 * (q0 >> 1) + 4 * c;
  uint32_t y1a = ub + U_PAD + (q1 & 1) * U_ODD + 16 * (q1 >> 1) + 4 * c;
#pragma unroll
  for (int i = 0; i < 4; i++) asm volatile("" : "+r"(bx[i]), "+r"(by[i]));
  asm volatile("" : "+r"(lb0), "+r"(lb1), "+r"(y0a), "+r"(y1a));
  mbar_wait(BAR(MB_UFULL));
  mbar_wait(BAR(MB_EMPTY + 15));
  TS(36);
  float acc[16][4];
  {
    uint32_t z09[8], z07[8], zm9[8], zm7[8];
#pragma unroll
    for (int i = 0; i < 8; i++) {
      uint32_t h[4];
      ldsm4(h, hb + 128 * i);
      float y0, y1, y2, y3, w0, w1, w2, w3;
      mma0(y0, y1, y2, y3, bx[0], bx[1], bx[2], bx[3], h[2], c < 2 ? h[3] : h[1]);
      mma0(w0, w1, w2, w3, bx[0], bx[1], bx[2], bx[3], h[1], c < 2 ? h[2] : h[0]);
      z09[i] = pack_bf(y0, y1); z07[i] = pack_bf(y2, y3);
      zm9[i] = pack_bf(w0, w1); zm7[i] = pack_bf(w2, w3);
    }
  uint32_t f3[3][4][4];
  {
    const uint32_t fa = tb + T_7 + 4 * (16 + x);
#pragma unroll
    for (int tt = 0; tt < 3; tt++)
#pragma unroll
      for (int D = 0; D < 4; D++) {
        const uint32_t a = fa + (tt == 0 ? 316 : (tt == 1 ? 320 : 0)) + 64 * D;
        f3[tt][D][0] = lds32(a); f3[tt][D][1] = lds32(a + 32); f3[tt][D][2] = lds32(a - 32); f3[tt][D][3] = lds32(a);
      }
  }
    float a[4][2][4];
#pragma unroll
    for (int kap = 0; kap < 4; kap++)
#pragma unroll
      for (int sg = 0; sg < 2; sg++)
#pragma unroll
        for (int bk = 3; bk >= kap; bk--) {
          const uint32_t(&q0_)[4] = f3[sg ? 2 : 0][bk - kap];
          const uint32_t(&q1_)[4] = f3[sg ? 2 : 1][bk - kap];
          float(&a0)[4] = a[bk][0];
          float(&a1)[4] = a[bk][1];
          if (sg == 0 && kap == 0) {
            mma0(a0[0], a0[1], a0[2], a0[3], q0_[0], q0_[1], q0_[2], q0_[3], z09[0], z09[1]);
            mma0(a1[0], a1[1], a1[2], a1[3], q1_[0], q1_[1], q1_[2], q1_[3], zm9[0], zm9[1]);
          } else {
            mma(a0[0], a0[1], a0[2], a0[3], q0_[0], q0_[1], q0_[2], q0_[3], sg ? zm7[2 * kap] : z09[2 * kap], sg ? zm7[2 * kap + 1] : z09[2 * kap + 1]);
            mma(a1[0], a1[1], a1[2], a1[3], q1_[0], q1_[1], q1_[2], q1_[3], sg ? z07[2 * kap] : zm9[2 * kap], sg ? z07[2 * kap + 1] : zm9[2 * kap + 1]);
          }
        }
    SPLIT();
#pragma unroll
    for (int i = 0; i < 8; i++) {
      uint32_t h[4];
      ldsm4(h, qa + 128 * i);
      const float ci[4] = {a[i >> 1][0][2 * (i & 1)], a[i >> 1][0][2 * (i & 1) + 1], a[i >> 1][1][2 * (i & 1)], a[i >> 1][1][2 * (i & 1) + 1]};
      mmac(acc[8 + i], h[0], h[1], h[2], h[3], lb0, lb1, ci);
    }
  }
  TS(44);
  {
    uint2 a5[10], a3[10];
    const uint32_t aa = tb + T_5 + 4 * (8 + 2 * g - 2 * c);
#pragma unroll
    for (int m = 0; m < 10; m++) { a5[m] = lds64(aa + 32 * m); a3[m] = lds64(aa + 384 + 32 * m); }
    uint32_t x5[12][2], x3[12][2];
    auto ygen = [&](int kap) {
#pragma unroll
      for (int hh = 0; hh < 2; hh++) {
        float y0, y1, y2, y3;
        mma0(y0, y1, y2, y3, by[0], by[1], by[2], by[3], lds32(y0a + 128 * kap + 64 * hh), lds32(y1a + 128 * kap + 64 * hh));
        x5[kap][hh] = pack_bf(y0, y1);
        x3[kap][hh] = pack_bf(y2, y3);
      }
    };
    ygen(11); ygen(10); ygen(9); ygen(8);
#pragma unroll
    for (int kap = 11; kap >= 0; kap--) {
      if (kap >= 4) ygen(kap - 4);
#pragma unroll
      for (int sg = 0; sg < 2; sg++)
#pragma unroll
        for (int i = 4; i >= 0; i--) {
          const int be = kap + 4 + i;
          if (be <= 15) {
            const uint2 &hi = sg ? a3[2 * i + 1] : a5[2 * i + 1], &lo = sg ? a3[2 * i] : a5[2 * i];
            const uint32_t b0 = sg ? x3[kap][0] : x5[kap][0], b1 = sg ? x3[kap][1] : x5[kap][1];
            if (be < 8 && i == 0 && sg == 0) mma0(acc[be][0], acc[be][1], acc[be][2], acc[be][3], hi.x, hi.y, lo.x, lo.y, b0, b1);
            else mma(acc[be][0], acc[be][1], acc[be][2], acc[be][3], hi.x, hi.y, lo.x, lo.y, b0, b1);
          }
        }
    }
  }
  TS(45);
  {
    const uint32_t st = tb + T_ST + lane * 8;
#pragma unroll
    for (int be = 4; be < 12; be++) sts64(st + 256 * be, pack_bf(acc[be][0], acc[be][1]), pack_bf(acc[be][2], acc[be][3]));
    SPLIT();
    uint32_t F[66], qd[8][4];
    const uint32_t fa = tb + T_D + 32 + 4 * x;
#pragma unroll
    for (int i = 0; i < 32; i++) {
      const int s = 120 - (i >> 2) - 8 * (i & 3);
      uint32_t(&q)[4] = qd[i & 7];
      ldsm4(q, qa + 16 * s);
      const int m = 16 * (i & 3) + 2 * (i >> 2);
      F[m] = lds32(fa + 32 * m); F[m + 1] = lds32(fa + 32 * m + 32);
#pragma unroll
      for (int be = 15; be >= 12; be--) {
        const int de = 8 * be - s;
        float(&a)[4] = (be >= 14 && !(i & 1)) ? acc[be - 4] : acc[be];
        if (de >= 0 && be >= 14 && i == 2 * (15 - be)) mma0(a[0], a[1], a[2], a[3], q[0], q[1], q[2], q[3], F[2 * de + 1], F[2 * de]);
        else if (de >= 0) mma(a[0], a[1], a[2], a[3], q[0], q[1], q[2], q[3], F[2 * de + 1], F[2 * de]);
      }
    }
#pragma unroll
    for (int i = 0; i < 8; i++) acc[14 + (i >> 2)][i & 3] += acc[10 + (i >> 2)][i & 3];
    F[64] = lds32(fa + 32 * 64); F[65] = lds32(fa + 32 * 65);
    uint32_t qp = qa + 128 * 11, sta = st + 256 * 10;
    uint4* yd = ydst + 7 * 32;
#pragma unroll
    for (int i = 0; i < 6; i++) ldsm4(qd[i], qp - 16 * i);
    uint2 sv = lds64(sta + 256);
    float ci[4] = {bf_lo(sv.x), bf_hi(sv.x), bf_lo(sv.y), bf_hi(sv.y)};
    float T[5][4];
#pragma unroll
    for (int i = 0; i < 16; i++) T[i >> 2][i & 3] = acc[12 + (i >> 2)][i & 3];
    nb_sync(NB_YZ, 160);
    TS(46);
#pragma unroll 1
    for (int bp = 5; bp >= 0; bp--) {
      uint32_t held[2];
#pragma unroll
      for (int o = 1; o >= 0; o--) {
#pragma unroll
        for (int k = 4; k >= 1; k--) mmac(T[k], qd[0][0], qd[0][1], qd[0][2], qd[0][3], F[16 * k + 1], F[16 * k], T[k - 1]);
        mmac(T[0], qd[0][0], qd[0][1], qd[0][2], qd[0][3], F[1], F[0], ci);
        ldsm4(qd[6], qp - 16 * 6);
        ldsm4(qd[7], qp - 16 * 7);
        sv = lds64(sta);
#pragma unroll
        for (int i = 1; i < 8; i++) {
#pragma unroll
          for (int k = 3; k >= 0; k--)
            mma(T[k][0], T[k][1], T[k][2], T[k][3], qd[i][0], qd[i][1], qd[i][2], qd[i][3], F[16 * k + 2 * i + 1], F[16 * k + 2 * i]);
          if (i < 7) ldsm4(qd[i - 1], qp - 128 - 16 * (i - 1));
          if (i == 2) {
            const uint32_t w0 = pack_bf(T[4][0], T[4][1]), w1 = pack_bf(T[4][2], T[4][3]);
            if (o) { held[0] = w0; held[1] = w1; }
            else st_x(yd, nz(w0), w1, held[0], held[1]);
          }
          if (i == 4) {
            if (2 * bp + o <= 4) sv = make_uint2(0, 0);
            ci[0] = bf_lo(sv.x); ci[1] = bf_hi(sv.x); ci[2] = bf_lo(sv.y); ci[3] = bf_hi(sv.y);
          }
        }
        qp -= 128; sta -= 256;
      }
      yd -= 32;
    }
#pragma unroll
    for (int B = 1; B >= 0; B--)
      st_x(ydst + B * 32, nz(pack_bf(T[2 * B][0], T[2 * B][1])), pack_bf(T[2 * B][2], T[2 * B][3]),
           pack_bf(T[2 * B + 1][0], T[2 * B + 1][1]), pack_bf(T[2 * B + 1][2], T[2 * B + 1][3]));
  }
}

__device__ __forceinline__ void dual_exp(const uint32_t* w, uint32_t* e) {
  const float L = 1.44268798828125f;
  uint32_t mx = bmax2(bmax2(w[0], w[1]), bmax2(w[2], w[3]));
  uint32_t mn = bmin2(bmin2(w[0], w[1]), bmin2(w[2], w[3]));
  mx = bmax2(mx, __shfl_xor_sync(0xffffffffu, mx, 1));
  mn = bmin2(mn, __shfl_xor_sync(0xffffffffu, mn, 1));
  mx = bmax2(mx, __shfl_xor_sync(0xffffffffu, mx, 2));
  mn = bmin2(mn, __shfl_xor_sync(0xffffffffu, mn, 2));
  const float mx0 = bf_lo(mx) * -L, mx1 = bf_hi(mx) * -L, mn0 = bf_lo(mn) * L, mn1 = bf_hi(mn) * L;
#pragma unroll
  for (int i = 0; i < 2; i++) {
    const float a0 = bf_lo(w[2 * i]), a1 = bf_hi(w[2 * i]), b0 = bf_lo(w[2 * i + 1]), b1 = bf_hi(w[2 * i + 1]);
    e[2 * i] = pack_bf(ex2(fmaf(a0, L, mx0)), ex2(fmaf(b0, L, mx0)));
    e[2 * i + 1] = pack_bf(ex2(fmaf(a1, L, mx1)), ex2(fmaf(b1, L, mx1)));
    e[4 + 2 * i] = pack_bf(ex2(fmaf(a0, -L, mn0)), ex2(fmaf(b0, -L, mn0)));
    e[5 + 2 * i] = pack_bf(ex2(fmaf(a1, -L, mn1)), ex2(fmaf(b1, -L, mn1)));
  }
}
__device__ __forceinline__ void normalise(uint32_t* e, const float (&s)[4]) {
  const uint32_t r = pack_bf(rcp(s[0]), rcp(s[2]));
  const __nv_bfloat162 rr = *(const __nv_bfloat162*)&r;
#pragma unroll
  for (int i = 0; i < 4; i++) {
    const __nv_bfloat162 v = __hmul2(*(const __nv_bfloat162*)&e[i], (i & 1) ? __high2bfloat162(rr) : __low2bfloat162(rr));
    e[i] = *(const uint32_t*)&v;
  }
}
__host__ __device__ constexpr uint64_t qdesc(uint32_t addr) { return mkdesc(addr, 128, 256, 0); }

__global__ void __launch_bounds__(NTHREADS, 1)
fused_kernel(const Params P, const __grid_constant__ CUtensorMap mx, const __grid_constant__ CUtensorMap mw,
             const __grid_constant__ CUtensorMap mo, const __grid_constant__ CUtensorMap mu,
             const __grid_constant__ CUtensorMap mout, const __grid_constant__ CUtensorMap mw4) {
  constexpr uint32_t sb = SB;
  const int tid = threadIdx.x, lane = tid & 31;
  const int warp = __shfl_sync(0xffffffffu, tid >> 5, 0);
  const int b = blockIdx.x, oct = b >> 3, i8 = b & 7;
  const int rt = oct < 8 ? oct : 15 - oct;
  const int hp = (oct >> 3) * 8 + i8;

  const int wg = warp >> 2, w = warp & 3;
  const int d = b * 4 + ((tid >> 5) & 3);
  if (tid < 384) {
    asm volatile("prefetch.tensormap [%0];" ::"l"(&mu) : "memory");
    asm volatile("prefetch.tensormap [%0];" ::"l"(&mw) : "memory");
    asm volatile("prefetch.tensormap [%0];" ::"l"(&mx) : "memory");
    asm volatile("prefetch.tensormap [%0];" ::"l"(&mw4) : "memory");
  }
  if (warp == 12) {
    if (lane == 0) {
#pragma unroll
      for (int i = 0; i < 9; i++) mbar_init(BAR(i), 1);
      asm volatile("fence.mbarrier_init.release.cluster;" ::: "memory");
    }
    __syncwarp();
    if (lane < 9) mbar_expect(BAR(0) + 8 * lane, lane == 5 ? 65536 : ((lane == 0 || lane > 5) ? 16384 : 28672));
    __syncwarp();
    e_tma3d(sb + OFF_W, &mw, BAR(MB_FULL), hp * 32, 0, 0);
    e_tma2d(sb + OFF_X + 3 * 16384, &mx, BAR(MB_FULL), 0, rt * 256);
    nb_arrive(NB_PROD, 192);
  } else if (warp == 13) {
    if (lane == 0) {
#pragma unroll
      for (int i = 9; i < 39; i++) mbar_init(BAR(i), i < MB_EMPTY ? 1 : (i < MB_AUX ? 4 : 8));
      asm volatile("fence.mbarrier_init.release.cluster;" ::: "memory");
    }
    __syncwarp();
    if (lane < 9) mbar_expect(BAR(MB_FULL + 8) + 8 * lane, lane < 8 ? 16384 : 131072);
    nb_arrive(NB_PROD, 192);
  }
  const KgenRaw raw = kgen_load(P, d, tid >> 7, lane);
  const unsigned short dsk = __ldg((const unsigned short*)P.Dskip + d);
  const uint32_t tb = sb + OFF_T + w * T_CH;
  const uint32_t kp = wg >= 2 ? sb + OFF_STG0 + 16384 + w * 2048 : ((tb + 127) & ~127u) + wg * 2048;
  const KgenAddr kad = kgen_addr(lane, wg == 3 ? sb + OFF_X + 32768 + w * 2048 : kp);
  if (wg == 1) nb_sync(NB_PROD, 192);
  if (warp == 12) {
#pragma unroll 1
    for (int kb = 1; kb < 4; kb++) {
      if (kb == U_AT) e_tma4d(sb + OFF_STG0, &mu, BAR(MB_URAW), i8 * 64, oct * 2);
      e_tma3d(sb + OFF_W + kb * 12288, &mw, BAR(MB_FULL) + 8 * kb, hp * 32, kb * 64, 0);
      e_tma2d(sb + OFF_X + (kb < 2 ? kb + 3 : kb - 2) * 16384, &mx, BAR(MB_FULL) + 8 * kb, kb * 64, rt * 256);
    }
    e_prefetch(P.x + (size_t)(rt * 256 + hp * 16) * 512, 16384);
    e_tma4d(sb + OFF_W + 4 * 12288, &mw4, BAR(MB_FULL + 4), hp * 32, 4);
    if (smem_u32(smem_raw) != SB) __trap();
    if (lane == 0) TS1(54);
  }
  float k[5][4], k2048, ksc;
  kgen_unit(raw, kad, blockIdx.y, k, k2048, ksc);
  TS(40 + wg);
  if ((fu(k[0][0]) & fu(k[1][0]) & fu(k[2][0]) & fu(k[3][0]) & fu(k[4][0])) == 0xffffffffu) sts32(kp, 0);
  if (wg == 3) {
    nb_sync(0, 512);
    if (warp == 12) {
      asm volatile("fence.proxy.async.shared::cta;" ::: "memory");
      e_tma2d(sb + OFF_X + 2 * 16384, &mx, BAR(MB_FULL + 4), 256, rt * 256);
    }
  } else if (wg) {
    nb_arrive(0, 512);
  }
  k2048 += __shfl_xor_sync(0xffffffffu, k2048, 16);
  k2048 += __shfl_xor_sync(0xffffffffu, k2048, 8);
  if (wg != 2) {
    uint32_t h[10];
#pragma unroll
    for (int j = 0; j < 10; j++) h[j] = hu(__floats2half2_rn(k[j >> 1][2 * (j & 1)], k[j >> 1][2 * (j & 1) + 1]));
    sts128(kp + lane * 16, h[0], h[1], h[2], h[3]);
    sts128(kp + 512 + lane * 16, h[4], h[5], h[6], h[7]);
    sts128(kp + 1024 + lane * 16, h[8], h[9], fu(k2048), fu(ksc));
  }
  if (wg == 0) { nb_arrive(NB_PREP, 512); nb_sync(0, 512); }
  else if (wg != 2) nb_arrive(NB_PREP, 512);
  else nb_sync(NB_PREP, 512);
  if (warp >= 12) {
    asm volatile("setmaxnreg.dec.sync.aligned.u32 32;");
    if (warp == 12) {
      uint32_t slot = sb + OFF_X + 3 * 16384;
#pragma unroll 1
      for (int n = 0; n < 11; n++) {
        mbar_spin(BAR(MB_EMPTY) + 8 * n);
        const int m = n + 5;
        e_tma2d(slot, &mx, BAR(MB_FULL) + 8 * m, (m & 7) * 64, rt * 256 + (m >> 3) * 128);
        slot = slot == sb + OFF_X + 4 * 16384 ? sb + OFF_X : slot + 16384;
        if (n == 7) {
          e_prefetch(P.wo + (size_t)b * 2048, 4096);
          asm volatile("prefetch.tensormap [%0];" ::"l"(&mo) : "memory");
          asm volatile("prefetch.tensormap [%0];" ::"l"(&mout) : "memory");
        }
      }
#pragma unroll 1
      for (int i = 0; i < 8; i++) {
        mbar_wait(BAR(MB_EMPTY + 10) + 8 * ((0x54332100u >> (4 * i)) & 7));
        const int w0 = (0x54736210u >> (4 * i)) & 7;
        e_tma3d(sb + OFF_W + w0 * 16384, &mo, BAR(MB_WO), 0, w0 * 64, (hp & 3) * 2);
      }
    } else {
      if (warp == 15) {
        const uint4 v0 = __ldg((const uint4*)P.wphi + hp * 64 + lane), v1 = __ldg((const uint4*)P.wphi + hp * 64 + 32 + lane);
        sts128(sb + OFF_PHI + (lane & 1) * 256 + (lane >> 1) * 16, v0.x, v0.y, v0.z, v0.w);
        sts128(sb + OFF_PHI + 512 + (lane & 1) * 256 + (lane >> 1) * 16, v1.x, v1.y, v1.z, v1.w);
        const uint32_t one = (((lane >> 3) ^ (lane >> 4)) & 1) ? 0u : ((lane & 1) ? 0x3F800000u : 0x3F80u);
        const int q = (lane >> 1) & 3;
        sts128(sb + OFF_EYE + lane * 16, q == 0 ? one : 0u, q == 1 ? one : 0u, q == 2 ? one : 0u, q == 3 ? one : 0u);
        sts64(sb + OFF_ONE + lane * 8, 0x3F803F80u, 0x3F803F80u);
        asm volatile("fence.proxy.async.shared::cta;" ::: "memory");
        nb_arrive(NB_KREAD, 160);
      }
      uint32_t* const cnt = (uint32_t*)(P.xs + X_CNT) + (warp == 13 ? i8 : (warp == 14 ? 8 + rt : 16 + oct)) * 32;
      const unsigned target = (ld_x32(cnt) & ~15u) + 16;
      if (warp != 14) {
        if (warp == 15) mbar_wait(BAR(MB_EMPTY + ZERO_STEP));
        uint4* pz = P.xs + (warp == 13 ? X_PART + (hp * 8 + rt) * 144 : X_Y + b * 1024);
#pragma unroll 1
        for (int i = lane; i < (warp == 13 ? 144 : 1024); i += 32) st_x(pz + i, 0, 0, 0, 0);
      }
      if (warp == 15) __syncwarp();
      else nb_sync(warp == 13 ? NB_INIT : NB_ODONE, warp == 13 ? 160 : 288);
      if (lane == 0) TS1(warp == 13 ? 49 : (warp == 14 ? 56 : 52));
      asm volatile("fence.proxy.async.shared::cta;" ::: "memory");
      if (lane == 0) asm volatile("red.release.gpu.global.add.u32 [%0], %1;" ::"l"(cnt), "r"(warp == 15 ? 2 : 1) : "memory");
      if (lane == 0) TS1(warp == 13 ? 50 : (warp == 14 ? 57 : 53));
      const uint32_t* pc = (warp == 13 && (lane & 1)) ? (uint32_t*)(P.xs + X_CNT) + (b >> 4) * 32 : cnt;
#pragma unroll 1
      for (int i = 0; i < SPIN_MAX; i++) {
        unsigned v;
        asm volatile("ld.acquire.gpu.global.u32 %0, [%1];" : "=r"(v) : "l"(pc) : "memory");
        if (__all_sync(0xffffffffu, (int)(v - target) >= 0)) break;
      }
      if (lane == 0) TS1(warp == 13 ? 51 : (warp == 14 ? 58 : 55));
      if (warp == 15) { nb_arrive(NB_YZ, 160); return; }
      asm volatile("fence.proxy.async.global;" ::: "memory");
      if (warp == 13) {
        mbar_wait(BAR(MB_EMPTY + 11));
        e_expect(BAR(MB_UFULL), 4 * U_CH);
        e_bulk(sb + OFF_U, P.xs + X_UT + b * (U_CH / 4), 4 * U_CH, BAR(MB_UFULL));
      } else {
        const uint4* src = P.xs + X_O + (rt * 4 + (hp >> 2)) * 4096;
        e_expect(BAR(MB_OA), 14336);
        e_bulk(sb + OFF_STG0, src + 3200, 14336, BAR(MB_OA));
        e_expect(BAR(MB_OC), 32768);
        e_bulk(sb + OFF_X + 32768, src, 32768, BAR(MB_OC));
        nb_sync(NB_BDONE, 288);
        asm volatile("fence.proxy.async.shared::cta;" ::: "memory");
        e_expect(BAR(MB_OB), 18432);
        e_bulk(sb + OFF_U, src + 2048, 18432, BAR(MB_OB));
      }
    }
    return;
  }

  const int t = tid & 127;
  const int g = lane >> 2, c = lane & 3;
  {
    if (wg == 2) {
      asm volatile("setmaxnreg.inc.sync.aligned.u32 160;");
#pragma unroll
      for (int j = 0; j < 5; j++) { k[j][0] *= ksc; k[j][1] *= ksc; k[j][2] *= ksc; k[j][3] *= ksc; }
#pragma unroll 1
      for (int q = 0; q < 3; q++) {
        const uint32_t src = (q == 2 ? kp : ((tb + 127) & ~127u) + q * 2048) + lane * 16;
        const uint4 v0 = lds128(src), v1 = lds128(src + 512), v2 = lds128(src + 1024);
        const uint32_t h[10] = {v0.x, v0.y, v0.z, v0.w, v1.x, v1.y, v1.z, v1.w, v2.x, v2.y};
#pragma unroll
        for (int j = 0; j < 10; j++) {
          const float2 f = __half22float2(*(const __half2*)&h[j]);
          k[j >> 1][2 * (j & 1)] = fmaf(f.x, uf(v2.w), k[j >> 1][2 * (j & 1)]);
          k[j >> 1][2 * (j & 1) + 1] = fmaf(f.y, uf(v2.w), k[j >> 1][2 * (j & 1) + 1]);
        }
        k2048 += uf(v2.z);
      }
#pragma unroll
      for (int o2 = 4; o2; o2 >>= 1) k2048 += __shfl_xor_sync(0xffffffffu, k2048, o2);
      if (lane == 0) k[0][0] += bf_lo(dsk);
      __syncwarp();
      if (lane == 0) mbar_arrive(BAR(MB_AUX));
      TS(34);
      build_tables(tb, lane, k, k2048);
      TS(35);
      uint4* const g_y = P.xs + X_Y;
      conv_channel(sb + OFF_U + w * U_CH, tb, lane, g_y + (size_t)d * 256 + lane);
      nb_arrive(NB_BDONE, 288);
      TS(37);
      const int lam = w * 8 + g;
      const uint4* src = g_y + (size_t)(oct * 32 + c * 8) * 256 + i8 * 32 + lam;
      uint4 v[8];
#pragma unroll 1
      for (int it = 0; it < SPIN_MAX; it++) {
        uint32_t m = 0xffffffffu;
#pragma unroll
        for (int i = 0; i < 8; i++) v[i] = ld_x(src + i * 256);
#pragma unroll
        for (int i = 0; i < 8; i++) m = min(m, v[i].x);
        if (__all_sync(0xffffffffu, m != 0)) break;
      }
      __nv_bfloat16* dst = P.out + (size_t)(i8 * 256 + (lam >> 2) * 16 + (lam & 3) * 2) * 1024 + 512 + oct * 32 + c * 8;
#pragma unroll
      for (int i = 0; i < 8; i++) *(uint4*)(dst + (size_t)((i >> 2) * 128 + ((i >> 1) & 1) * 8 + (i & 1)) * 1024) = tr_row(v, i);
      TS(38);
      GT(63);
      if (w == 0) TSDUMP(32);
      return;
    }
    if (wg == 1) {
      mbar_wait(BAR(MB_URAW));
      TS(48);
      uint4* dst = P.xs + X_UT + (i8 * 64 + g) * (U_CH / 16) + (w & 1) * (U_ODD / 16) + U_PAD / 16 + oct * 8 + (w >> 1) * 4 + c;
      const int ln = ((lane >> 1) & 3) + 4 * (lane & 1);
      uint32_t r[8][4];
#pragma unroll
      for (int i = 0; i < 8; i++) ldsm4t(r[i], sb + OFF_STG0 + w * 4096 + ((lane >> 3) * 8 + ln) * 128 + ((i ^ ln) << 4));
#pragma unroll
      for (int i = 0; i < 8; i++) dst[i * (U_CH / 2)] = make_uint4(r[i][0], r[i][1], r[i][2], r[i][3]);
      nb_arrive(NB_INIT, 160);
      if (lane == 0) mbar_arrive(BAR(MB_AUX));
      mbar_wait(BAR(MB_EMPTY + 4));
      mbar_spin(BAR(MB_EMPTY + 6));
    }
    TS(wg * 16 + 1);
  }

  float acc[2][48];
  {
    uint32_t fb = BAR(MB_FULL) + 64 * wg;
    uint32_t da = (uint32_t)mkdesc(sb + OFF_X, 16, 0, 0) + (wg ? 1024 : 3072), db = (uint32_t)mkdesc(sb + OFF_W, 4096, 0, 0);
    constexpr uint64_t ha = mkdesc(0, 0, 1024, 1), hb = mkdesc(0, 0, 512, 2);
    mbar_spin(fb);
    TS(wg * 16 + 2);
#pragma unroll 1
    for (int kb = 0; kb < 8; kb++) {
      WG_FENCE();
#pragma unroll
      for (int k = 0; k < 4; k++) {
        wgmma_ss_n96(acc[0], ha | (da + 2 * k), hb | (db + 64 * k), k ? 1 : kb);
        wgmma_ss_n96(acc[1], ha | (da + 2 * k + 512), hb | (db + 64 * k), k ? 1 : kb);
      }
      WG_COMMIT();
      if (kb < 7) mbar_spin(fb + 8);
      WG_WAIT(1);
      if (kb > 0) e_arrive(fb + 8 * (MB_EMPTY - MB_FULL - 1));
      fb += 8; db += 768;
      da = da == (uint32_t)mkdesc(sb + OFF_X + 65536, 16, 0, 0) ? da - 4096 : da + 1024;
    }
    if (wg == 0) nb_sync(NB_KREAD, 160);
    WG_WAIT(0);
    e_arrive(fb + 8 * (MB_EMPTY - MB_FULL - 1));
    mbar_spin(fb + 8 * (MB_EMPTY - MB_FULL - 1));
  }
  TS(wg * 16 + 3);
  asm volatile("setmaxnreg.inc.sync.aligned.u32 160;");

  constexpr uint32_t stg0 = sb + OFF_STG0, stg1 = sb + OFF_X + 32768;
  uint4* const g_part = P.xs + X_PART;
  uint4* const g_o = P.xs + X_O;
  constexpr uint32_t kvs = stg0;
  auto pack8 = [](const float* a) { return make_uint4(pack_bf(a[0], a[1]), pack_bf(a[2], a[3]), pack_bf(a[4], a[5]), pack_bf(a[6], a[7])); };
  auto feat = [&](const uint4 (&af)[4], float (&p)[4][8]) {
    WG_FENCE();
#pragma unroll
    for (int u = 0; u < 4; u++) wgmma_rs_n16(p[u], af[u], qdesc(sb + OFF_PHI + (u & 1) * 512), 0);
    WG_COMMIT();
  };
  auto packp = [](const float (&p)[4][8], uint32_t (&pw)[16]) {
#pragma unroll
    for (int i = 0; i < 16; i++) pw[i] = pack_bf(p[i >> 2][(i & 1) + 2 * (i & 2)], p[i >> 2][(i & 1) + 2 * (i & 2) + 2]);
  };
  auto contract = [&](float (&kc)[20], uint32_t stg, int acc_in) {
    WG_FENCE();
#pragma unroll
    for (int s = 0; s < 8; s++) wgmma_ss_n40(kc, qdesc(stg + s * SLAB), qdesc(stg + s * SLAB + 2048), s ? 1 : acc_in);
    WG_COMMIT();
    WG_WAIT(0);
  };
  uint32_t eq[32];
  {
    uint4 af[4], aq[4], vp[4];
    float p[4][8];
#pragma unroll
    for (int u = 0; u < 4; u++) af[u] = pack8(acc[u >> 1] + 16 + 8 * (u & 1));
    feat(af, p);
#pragma unroll
    for (int u = 0; u < 4; u++) { aq[u] = pack8(acc[u >> 1] + 8 * (u & 1)); vp[u] = pack8(acc[u >> 1] + 32 + 8 * (u & 1)); }
    WG_WAIT(0);
    uint32_t pw[16], ek[32];
    packp(p, pw);
#pragma unroll
    for (int u = 0; u < 4; u++) dual_exp(pw + 4 * u, ek + 8 * u);
    TS(wg * 16 + 12);
    mbar_wait(BAR(MB_AUX));
    float rs[8][4];
    WG_FENCE();
#pragma unroll
    for (int i = 0; i < 8; i++) wgmma_rs_n8(rs[i], make_uint4(ek[4 * i], ek[4 * i + 1], ek[4 * i + 2], ek[4 * i + 3]), qdesc(sb + OFF_ONE), 0);
    WG_COMMIT();
    feat(aq, p);
    const uint32_t sl = (wg ? stg1 : stg0) + w * SLAB + lane * 16;
#pragma unroll
    for (int i = 0; i < 4; i++) stsm4(sl + (i >> 1) * 4 * SLAB + 2048 + (i & 1) * 512, vp[i].x, vp[i].y, vp[i].z, vp[i].w);
    sts128(sl + (lane >> 4) * (4 * SLAB - 256) + 3072, 0x3F803F80u, 0x3F803F80u, 0x3F803F80u, 0x3F803F80u);
    WG_WAIT(1);
#pragma unroll
    for (int i = 0; i < 8; i++) {
      normalise(ek + 4 * i, rs[i]);
      stsm4(sl + (i >> 2) * 4 * SLAB + (i & 3) * 512, ek[4 * i], ek[4 * i + 1], ek[4 * i + 2], ek[4 * i + 3]);
    }
    asm volatile("fence.proxy.async.shared::cta;" ::: "memory");
    TS(wg * 16 + 13);
    if (wg) {
      nb_arrive(NB_ST0, 256);
    } else {
      float kc[20];
      uint4* pp = g_part + (size_t)(hp * 8 + rt) * 144 + t;
      uint32_t* pz = (uint32_t*)(pp - t + 128) + w * 16 + c * 8 + g;
      asm volatile("" : "+l"(pp), "+l"(pz));
      nb_sync(NB_WG0, 128);
      contract(kc, stg0, 0);
      mbar_wait(BAR(MB_UFULL));
      TS(15);
      nb_sync(NB_ST0, 256);
      contract(kc, stg1, 1);
      TS(6);
      float kv[8];
#pragma unroll
      for (int i = 0; i < 8; i++) kv[i] = w & 2 ? kc[8 + i] : kc[i];
      st_x(pp, nz(pack_bf(kv[0], kv[1])), pack_bf(kv[2], kv[3]), pack_bf(kv[4], kv[5]), pack_bf(kv[6], kv[7]));
      if (c < 2) st_x32(pz, nz(fu(c ? kc[18] : kc[16])));
      TS(5);
    }
    SPLIT();
    WG_WAIT(0);
    packp(p, pw);
#pragma unroll
    for (int u = 0; u < 4; u++) dual_exp(pw + 4 * u, eq + 8 * u);
    SPLIT();
  }
  TS(wg * 16 + 4);
  if (wg == 1) {
    mbar_wait(BAR(MB_UFULL));
    const uint4* ps = g_part + (size_t)hp * 8 * 144 + t;
    const uint32_t* zs = (const uint32_t*)(g_part + (size_t)(hp * 8 + (lane >> 4) * 4) * 144 + 128) + w * 16 + (lane & 15);
    uint4 v[8];
    uint32_t zv[4];
#pragma unroll 1
    for (int it = 0; it < SPIN_MAX; it++) {
#pragma unroll
      for (int i = 0; i < 8; i++) v[i] = ld_x(ps + i * 144);
#pragma unroll
      for (int i = 0; i < 4; i++) zv[i] = ld_x32(zs + i * 576);
      uint32_t m = min(min(zv[0], zv[1]), min(zv[2], zv[3]));
#pragma unroll
      for (int i = 0; i < 8; i++) m = min(m, v[i].x);
      if (__all_sync(0xffffffffu, m != 0)) break;
    }
    float s[8];
    WG_FENCE();
#pragma unroll
    for (int r = 0; r < 8; r++) wgmma_rs_n16(s, v[r], qdesc(sb + OFF_EYE), r);
    WG_COMMIT();
    float zsum = (uf(zv[0]) + uf(zv[1])) + (uf(zv[2]) + uf(zv[3]));
    zsum += __shfl_xor_sync(0xffffffffu, zsum, 16);
    const uint32_t z1 = pack_bf(zsum, 1.f);
    if (lane < 16) sts128(kvs + w * 768 + 512 + lane * 16, z1, z1, z1, z1);
    WG_WAIT(0);
    stsm4(kvs + w * 768 + lane * 16, pack_bf(s[0], s[1]), pack_bf(s[2], s[3]), pack_bf(s[4], s[5]), pack_bf(s[6], s[7]));
    asm volatile("fence.proxy.async.shared::cta;" ::: "memory");
    TS(22);
  }
  nb_sync(NB_KV, 256);
  {
    float n[8][12];
    WG_FENCE();
#pragma unroll
    for (int i = 0; i < 8; i++) wgmma_rs_n24(n[i], make_uint4(eq[4 * i], eq[4 * i + 1], eq[4 * i + 2], eq[4 * i + 3]), qdesc(kvs + (i & 3) * 768), 0);
    WG_COMMIT();
    uint32_t* od = (uint32_t*)(g_o + (size_t)((rt * 4 + wg * 2) * 32 + hp * 2) * 128) + w * 64 + lane;
    WG_WAIT(0);
#pragma unroll
    for (int u = 0; u < 4; u++) {
      float(&np)[12] = n[2 * u];
      const float(&nm)[12] = n[2 * u + 1];
      const float q0 = np[9] * rcp(nm[9]), q1 = np[11] * rcp(nm[11]);
      const float r0 = rcp(fmaf(nm[8], q0, fmaf(np[9], 1e-6f, np[8]))), r1 = rcp(fmaf(nm[10], q1, fmaf(np[11], 1e-6f, np[10])));
#pragma unroll
      for (int i = 0; i < 8; i++) np[i] = fmaf(nm[i], (i & 2) ? q1 : q0, np[i]);
      uint32_t* o = od + (u >> 1) * 16384 + (u & 1) * 512;
      o[0] = pack_bf(np[0] * r0, np[1] * r0);
      o[32] = pack_bf(np[2] * r1, np[3] * r1);
      o[256] = pack_bf(np[4] * r0, np[5] * r0);
      o[288] = pack_bf(np[6] * r1, np[7] * r1);
      if (u == 1) SPLIT();
    }
  }
  TS(wg * 16 + 7);
  nb_arrive(NB_ODONE, 288);
  if (wg) { if (w == 0) TSDUMP(16); return; }
  mbar_wait(BAR(MB_WO));
  mbar_wait(BAR(MB_OA));
  TS(8);
  nb_sync(NB_BDONE, 288);
  TS(9);
  float oc[64];
  {
    constexpr uint64_t ha = mkdesc(0, 0, 128, 0), hb = mkdesc(0, 0, 1024, 1);
    constexpr uint32_t da0 = (uint32_t)mkdesc(stg1, 1024, 0, 0), db0 = (uint32_t)mkdesc(sb + OFF_W, 8192, 0, 0);
#pragma unroll 1
    for (int j = 0; j < 8; j++) {
      const int kb = (j + 7) & 7;
      if ((j & 3) == 1) mbar_spin(j == 1 ? BAR(MB_OC) : BAR(MB_OB));
      WG_FENCE();
#pragma unroll
      for (int k = 0; k < 4; k++) wgmma_ss_n128(oc, ha | (da0 + 512 * kb + 128 * k), hb | (db0 + 1024 * kb + 128 * k), k ? 1 : j);
      WG_COMMIT();
    }
    WG_WAIT(0);
  }
  TS(10);
  const uint32_t ot = ((sb + OFF_T + 1023) & ~1023u) + w * 4096;
#pragma unroll
  for (int hf = 0; hf < 2; hf++) {
#pragma unroll
    for (int i = 8 * hf; i < 8 * hf + 8; i += 2)
      stsm4(ot + hf * 2048 + (lane & 15) * 128 + (((i + (lane >> 4)) ^ lane) & 7) * 16, pack_bf(oc[4 * i], oc[4 * i + 1]),
            pack_bf(oc[4 * i + 2], oc[4 * i + 3]), pack_bf(oc[4 * i + 4], oc[4 * i + 5]), pack_bf(oc[4 * i + 6], oc[4 * i + 7]));
    asm volatile("fence.proxy.async.shared::cta;" ::: "memory");
    __syncwarp();
    e_store2d(&mout, ot + hf * 2048, (hp & 3) * 128 + hf * 64, (rt * 4 + (hp >> 2)) * 64 + w * 16);
  }
  asm volatile(ELECT "cp.async.bulk.commit_group;\n@p cp.async.bulk.wait_group.read 0;\n}\n" ::: "memory");
  TS(wg * 16 + 11);
  GT(61 + wg);
  if (w == 0) TSDUMP(0);
  if (w == 1) TSDUMP(48);
}

typedef CUresult (*EncodeFn)(CUtensorMap*, CUtensorMapDataType, cuuint32_t, void*, const cuuint64_t*, const cuuint64_t*,
                             const cuuint32_t*, const cuuint32_t*, CUtensorMapInterleave, CUtensorMapSwizzle,
                             CUtensorMapL2promotion, CUtensorMapFloatOOBfill);

}

extern "C" void kernel_launch(void* const* d_in, const int* in_sizes, int n_in, void* d_out, int out_size) {
  (void)in_sizes; (void)n_in; (void)out_size;
  void* fn = nullptr;
  cudaDriverEntryPointQueryResult qr;
  cudaGetDriverEntryPoint("cuTensorMapEncodeTiled", &fn, cudaEnableDefault, &qr);
  EncodeFn enc = (EncodeFn)fn;
  CUtensorMap mx, mw, mo, mu, mout, mw4;
  const cuuint32_t es[5] = {1, 1, 1, 1, 1};
  {
    cuuint64_t dims[2] = {512, 2048}, st[1] = {1024};
    cuuint32_t box[2] = {64, 128};
    enc(&mx, CU_TENSOR_MAP_DATA_TYPE_BFLOAT16, 2, d_in[0], dims, st, box, es, CU_TENSOR_MAP_INTERLEAVE_NONE,
        CU_TENSOR_MAP_SWIZZLE_128B, CU_TENSOR_MAP_L2_PROMOTION_L2_128B, CU_TENSOR_MAP_FLOAT_OOB_FILL_NONE);
  }
  {
    cuuint64_t dims[3] = {512, 512, 3}, st[2] = {3072, 1024};
    cuuint32_t box[3] = {32, 64, 3};
    enc(&mw, CU_TENSOR_MAP_DATA_TYPE_BFLOAT16, 3, d_in[1], dims, st, box, es, CU_TENSOR_MAP_INTERLEAVE_NONE,
        CU_TENSOR_MAP_SWIZZLE_64B, CU_TENSOR_MAP_L2_PROMOTION_L2_128B, CU_TENSOR_MAP_FLOAT_OOB_FILL_NONE);
  }
  {
    cuuint64_t dims[3] = {64, 512, 8}, st[2] = {1024, 128};
    cuuint32_t box[3] = {64, 64, 2};
    enc(&mo, CU_TENSOR_MAP_DATA_TYPE_BFLOAT16, 3, d_in[3], dims, st, box, es, CU_TENSOR_MAP_INTERLEAVE_NONE,
        CU_TENSOR_MAP_SWIZZLE_128B, CU_TENSOR_MAP_L2_PROMOTION_L2_128B, CU_TENSOR_MAP_FLOAT_OOB_FILL_NONE);
  }
  {
    cuuint64_t dims[4] = {512, 4, 16, 32}, st[3] = {16384, 1024, 65536};
    cuuint32_t box[4] = {64, 4, 16, 2};
    enc(&mu, CU_TENSOR_MAP_DATA_TYPE_BFLOAT16, 4, d_in[4], dims, st, box, es, CU_TENSOR_MAP_INTERLEAVE_NONE,
        CU_TENSOR_MAP_SWIZZLE_128B, CU_TENSOR_MAP_L2_PROMOTION_L2_128B, CU_TENSOR_MAP_FLOAT_OOB_FILL_NONE);
  }
  {
    cuuint64_t dims[2] = {1024, 2048}, st[1] = {2048};
    cuuint32_t box[2] = {64, 16};
    enc(&mout, CU_TENSOR_MAP_DATA_TYPE_BFLOAT16, 2, d_out, dims, st, box, es, CU_TENSOR_MAP_INTERLEAVE_NONE,
        CU_TENSOR_MAP_SWIZZLE_128B, CU_TENSOR_MAP_L2_PROMOTION_NONE, CU_TENSOR_MAP_FLOAT_OOB_FILL_NONE);
  }
  {
    cuuint64_t dims[4] = {512, 64, 3, 8}, st[3] = {3072, 1024, 64 * 3072};
    cuuint32_t box[4] = {32, 64, 3, 4};
    enc(&mw4, CU_TENSOR_MAP_DATA_TYPE_BFLOAT16, 4, d_in[1], dims, st, box, es, CU_TENSOR_MAP_INTERLEAVE_NONE,
        CU_TENSOR_MAP_SWIZZLE_64B, CU_TENSOR_MAP_L2_PROMOTION_L2_128B, CU_TENSOR_MAP_FLOAT_OOB_FILL_NONE);
  }
  Params P;
  P.x = (const __nv_bfloat16*)d_in[0];
  P.wphi = (const __nv_bfloat16*)d_in[2];
  P.wo = (const __nv_bfloat16*)d_in[3];
  P.logA = (const __nv_bfloat16*)d_in[5];
  P.Aim = (const __nv_bfloat16*)d_in[6];
  P.Cre = (const __nv_bfloat16*)d_in[7];
  P.Cim = (const __nv_bfloat16*)d_in[8];
  P.logdt = (const __nv_bfloat16*)d_in[9];
  P.Dskip = (const __nv_bfloat16*)d_in[10];
  P.out = (__nv_bfloat16*)d_out;
  cudaGetSymbolAddress((void**)&P.xs, g_x);
  P.ts = nullptr;
  cudaFuncSetAttribute(fused_kernel, cudaFuncAttributeMaxDynamicSharedMemorySize, SMEM_BYTES);
  fused_kernel<<<NCTA, NTHREADS, SMEM_BYTES>>>(P, mx, mw, mo, mu, mout, mw4);
}
```

```cpp
#include <cuda_runtime.h>
#include <cuda_bf16.h>
#include <cuda_fp16.h>
#include <cuda.h>
#include <stdint.h>

#define DBG_TS 0

namespace {

constexpr int NTHREADS = 512;
constexpr int NCTA = 128;
constexpr int OFF_W = 0;
constexpr int OFF_X = 98304;
constexpr int OFF_U = OFF_X + 65536;
constexpr int U_CH = 4416, U_ODD = 2240, U_PAD = 128;
constexpr int OFF_STG0 = OFF_U + 18432;
constexpr int SLAB = 3328;
constexpr int OFF_T = OFF_STG0 + 8 * SLAB;
constexpr int T_CH = 5216;
constexpr int T_D = 0;
constexpr int T_5 = 2144;
constexpr int T_3 = T_5 + 384;
constexpr int T_7 = T_5 + 1024;
constexpr int T_9 = T_7 + 320;
constexpr int T_KC = T_9 + 320;
constexpr int T_ST = T_5 - 1024;
constexpr int OFF_PHI = OFF_T + 4 * T_CH;
constexpr int OFF_EYE = OFF_PHI + 1024, OFF_ONE = OFF_EYE + 512;
constexpr int OFF_BAR = OFF_ONE + 256;
constexpr int SMEM_BYTES = OFF_BAR + 512 + 256 * DBG_TS;
constexpr uint32_t SB = 1024;
static_assert(T_KC + 2 * 656 <= T_CH, "table size");
static_assert(SMEM_BYTES <= 232448, "smem");
constexpr int MB_URAW = 0, MB_FULL = 1  , MB_WO = 17, MB_UFULL = 18, MB_OA = 19, MB_OB = 20, MB_OC = 21,
              MB_EMPTY = 22  , MB_AUX = 38;
__host__ __device__ constexpr uint32_t BAR(int i) { return SB + OFF_BAR + 8 * i; }
constexpr int NB_WG0 = 1, NB_ODONE = 2, NB_ST0 = 3  , NB_KV = 5, NB_YZ = 6, NB_INIT = 7, NB_PREP = 8, NB_PROD = 9, NB_KREAD = 10, NB_BDONE = 11, NB_OREL = 12  ;
#define U_AT 2
#define ZERO_STEP 12
constexpr int SPIN_MAX = 1 << 16;

constexpr int X_CNT = 0;
constexpr int X_PART = 256;
constexpr int X_O = X_PART + 16 * 8 * 144;
constexpr int X_Y = X_O + 32 * 32 * 128;
constexpr int X_UT = X_Y + 512 * 8 * 32;
constexpr int X_SIZE = X_UT + 512 * (U_CH / 16);
__device__ __align__(128) uint4 g_x[X_SIZE];
extern __shared__ uint8_t smem_raw[];
#define TS(i) do {} while (0)
#define TS1(i) do {} while (0)
#define GT(i) do {} while (0)
#define TSDUMP(base) do {} while (0)

__device__ __forceinline__ uint32_t smem_u32(const void* p) { return (uint32_t)__cvta_generic_to_shared(p); }
__device__ __forceinline__ void mbar_arrive(uint32_t b) {
  asm volatile("mbarrier.arrive.shared::cta.b64 _, [%0];" ::"r"(b) : "memory");
}
__device__ __forceinline__ void mbar_wait(uint32_t b) {
  uint32_t done = 0;
#pragma unroll 1
  for (int i = 0; i < SPIN_MAX && !done; i++) {
    asm volatile("{\n.reg .pred p;\nmbarrier.try_wait.parity.shared::cta.b64 p, [%1], 0, 4000;\nselp.u32 %0, 1, 0, p;\n}\n"
                 : "=r"(done) : "r"(b) : "memory");
  }
}
__device__ __forceinline__ void mbar_spin(uint32_t b) {
  uint32_t done = 0;
#pragma unroll 1
  for (int i = 0; i < (SPIN_MAX << 4) && !done; i++) {
    asm volatile("{\n.reg .pred p;\nmbarrier.try_wait.parity.shared::cta.b64 p, [%1], 0;\nselp.u32 %0, 1, 0, p;\n}\n"
                 : "=r"(done) : "r"(b) : "memory");
  }
}
__device__ __forceinline__ void mbar_init(uint32_t b, int n) {
  asm volatile("mbarrier.init.shared::cta.b64 [%0], %1;" ::"r"(b), "r"(n) : "memory");
}
__device__ __forceinline__ void mbar_expect(uint32_t b, int bytes) {
  asm volatile("mbarrier.arrive.expect_tx.shared::cta.b64 _, [%0], %1;" ::"r"(b), "r"(bytes) : "memory");
}
__device__ __forceinline__ void nb_sync(int id, int n) { asm volatile("bar.sync %0, %1;" ::"r"(id), "r"(n) : "memory"); }
__device__ __forceinline__ void nb_arrive(int id, int n) { asm volatile("bar.arrive %0, %1;" ::"r"(id), "r"(n) : "memory"); }
#define ELECT "{\n.reg .pred p;\nelect.sync _|p, 0xffffffff;\n@p "
__device__ __forceinline__ void e_arrive(uint32_t b) {
  asm volatile(ELECT "mbarrier.arrive.shared::cta.b64 _, [%0];\n}\n" ::"r"(b) : "memory");
}
__device__ __forceinline__ void e_expect(uint32_t b, int bytes) {
  asm volatile(ELECT "mbarrier.arrive.expect_tx.shared::cta.b64 _, [%0], %1;\n}\n" ::"r"(b), "r"(bytes) : "memory");
}
__device__ __forceinline__ void e_tma2d(uint32_t dst, const CUtensorMap* m, uint32_t bar, int c0, int c1) {
  asm volatile(ELECT "cp.async.bulk.tensor.2d.shared::cluster.global.mbarrier::complete_tx::bytes [%0], [%1, {%3,%4}], [%2];\n}\n"
               ::"r"(dst), "l"(m), "r"(bar), "r"(c0), "r"(c1) : "memory");
}
__device__ __forceinline__ void e_tma3d(uint32_t dst, const CUtensorMap* m, uint32_t bar, int c0, int c1, int c2) {
  asm volatile(ELECT "cp.async.bulk.tensor.3d.shared::cluster.global.mbarrier::complete_tx::bytes [%0], [%1, {%3,%4,%5}], [%2];\n}\n"
               ::"r"(dst), "l"(m), "r"(bar), "r"(c0), "r"(c1), "r"(c2) : "memory");
}
__device__ __forceinline__ void e_tma4d(uint32_t dst, const CUtensorMap* m, uint32_t bar, int c0, int c3) {
  asm volatile(ELECT "cp.async.bulk.tensor.4d.shared::cluster.global.mbarrier::complete_tx::bytes [%0], [%1, {%3,%5,%5,%4}], [%2];\n}\n"
               ::"r"(dst), "l"(m), "r"(bar), "r"(c0), "r"(c3), "r"(0) : "memory");
}
__device__ __forceinline__ void e_bulk(uint32_t dst, const void* src, int bytes, uint32_t bar) {
  asm volatile(ELECT "cp.async.bulk.shared::cluster.global.mbarrier::complete_tx::bytes [%0], [%1], %2, [%3];\n}\n"
               ::"r"(dst), "l"(src), "r"(bytes), "r"(bar) : "memory");
}
__device__ __forceinline__ void e_prefetch(const void* p, int bytes) {
  asm volatile(ELECT "cp.async.bulk.prefetch.L2.global [%0], %1;\n}\n" ::"l"(p), "r"(bytes) : "memory");
}
__device__ __forceinline__ void e_store2d(const CUtensorMap* m, uint32_t src, int c0, int c1) {
  asm volatile(ELECT "cp.async.bulk.tensor.2d.global.shared::cta.bulk_group [%0, {%2,%3}], [%1];\n}\n"
               ::"l"(m), "r"(src), "r"(c0), "r"(c1) : "memory");
}
__host__ __device__ constexpr uint64_t mkdesc(uint32_t addr, uint32_t lbo, uint32_t sbo, int swz) {
  return (uint64_t)((addr & 0x3FFFF) >> 4) | ((uint64_t)(lbo >> 4) << 16) | ((uint64_t)(sbo >> 4) << 32) |
         ((uint64_t)swz << 62);
}
#define SPLIT() asm volatile("{\n.reg .pred p;\nsetp.eq.u32 p, %0, %1;\n@p exit;\n}\n" ::"r"(blockIdx.y), "n"(__LINE__) : "memory")
#define WG_FENCE() asm volatile("wgmma.fence.sync.aligned;" ::: "memory")
#define WG_COMMIT() asm volatile("wgmma.commit_group.sync.aligned;" ::: "memory")
#define WG_WAIT(n) asm volatile("wgmma.wait_group.sync.aligned " #n ";" ::: "memory")

__device__ __forceinline__ void mma(float& d0, float& d1, float& d2, float& d3, uint32_t a0, uint32_t a1, uint32_t a2,
                                    uint32_t a3, uint32_t b0, uint32_t b1) {
  asm volatile("mma.sync.aligned.m16n8k16.row.col.f32.bf16.bf16.f32 {%0,%1,%2,%3},{%4,%5,%6,%7},{%8,%9},{%0,%1,%2,%3};"
               : "+f"(d0), "+f"(d1), "+f"(d2), "+f"(d3)
               : "r"(a0), "r"(a1), "r"(a2), "r"(a3), "r"(b0), "r"(b1));
}
__device__ __forceinline__ void mmac(float (&d)[4], uint32_t a0, uint32_t a1, uint32_t a2, uint32_t a3, uint32_t b0,
                                     uint32_t b1, const float (&c)[4]) {
  asm volatile("mma.sync.aligned.m16n8k16.row.col.f32.bf16.bf16.f32 {%0,%1,%2,%3},{%4,%5,%6,%7},{%8,%9},{%10,%11,%12,%13};"
               : "=f"(d[0]), "=f"(d[1]), "=f"(d[2]), "=f"(d[3])
               : "r"(a0), "r"(a1), "r"(a2), "r"(a3), "r"(b0), "r"(b1), "f"(c[0]), "f"(c[1]), "f"(c[2]), "f"(c[3]));
}
__device__ __forceinline__ void mma_p(int p, float (&d)[4], uint32_t a0, uint32_t a1, uint32_t a2, uint32_t a3, uint32_t b0, uint32_t b1) {
  asm volatile("{\n.reg .pred q;\nsetp.ne.b32 q, %10, 0;\n"
               "@q mma.sync.aligned.m16n8k16.row.col.f32.bf16.bf16.f32 {%0,%1,%2,%3},{%4,%5,%6,%7},{%8,%9},{%0,%1,%2,%3};\n}\n"
               : "+f"(d[0]), "+f"(d[1]), "+f"(d[2]), "+f"(d[3])
               : "r"(a0), "r"(a1), "r"(a2), "r"(a3), "r"(b0), "r"(b1), "r"(p));
}
__device__ __forceinline__ void mmac_p(int p, float (&d)[4], uint32_t a0, uint32_t a1, uint32_t a2, uint32_t a3, uint32_t b0,
                                       uint32_t b1, const float (&c)[4]) {
  asm volatile("{\n.reg .pred q;\nsetp.ne.b32 q, %14, 0;\n"
               "@q mma.sync.aligned.m16n8k16.row.col.f32.bf16.bf16.f32 {%0,%1,%2,%3},{%4,%5,%6,%7},{%8,%9},{%10,%11,%12,%13};\n}\n"
               : "+f"(d[0]), "+f"(d[1]), "+f"(d[2]), "+f"(d[3])
               : "r"(a0), "r"(a1), "r"(a2), "r"(a3), "r"(b0), "r"(b1), "f"(c[0]), "f"(c[1]), "f"(c[2]), "f"(c[3]), "r"(p));
}
__device__ __forceinline__ void mma_h(float (&d)[4], const uint32_t (&a)[4], uint32_t b0, uint32_t b1) {
  asm volatile("mma.sync.aligned.m16n8k16.row.col.f32.f16.f16.f32 {%0,%1,%2,%3},{%4,%5,%6,%7},{%8,%9},{%0,%1,%2,%3};"
               : "+f"(d[0]), "+f"(d[1]), "+f"(d[2]), "+f"(d[3]) : "r"(a[0]), "r"(a[1]), "r"(a[2]), "r"(a[3]), "r"(b0), "r"(b1));
}
__device__ __forceinline__ void mma0(float& d0, float& d1, float& d2, float& d3, uint32_t a0, uint32_t a1, uint32_t a2,
                                     uint32_t a3, uint32_t b0, uint32_t b1) {
  asm volatile("mma.sync.aligned.m16n8k16.row.col.f32.bf16.bf16.f32 {%0,%1,%2,%3},{%4,%5,%6,%7},{%8,%9},{%10,%10,%10,%10};"
               : "=f"(d0), "=f"(d1), "=f"(d2), "=f"(d3)
               : "r"(a0), "r"(a1), "r"(a2), "r"(a3), "r"(b0), "r"(b1), "f"(0.f));
}
__device__ __forceinline__ uint32_t pack_bf(float lo, float hi) {
  uint32_t r;
  asm("cvt.rn.bf16x2.f32 %0, %1, %2;" : "=r"(r) : "f"(hi), "f"(lo));
  return r;
}
__device__ __forceinline__ float bf_lo(uint32_t w) { return __uint_as_float(w << 16); }
__device__ __forceinline__ float bf_hi(uint32_t w) { return __uint_as_float(w & 0xffff0000u); }
__device__ __forceinline__ float bf_round(float x) { return __bfloat162float(__float2bfloat16_rn(x)); }
__device__ __forceinline__ uint32_t bmax2(uint32_t a, uint32_t b) {
  uint32_t r; asm("max.bf16x2 %0, %1, %2;" : "=r"(r) : "r"(a), "r"(b)); return r;
}
__device__ __forceinline__ uint32_t bmin2(uint32_t a, uint32_t b) {
  uint32_t r; asm("min.bf16x2 %0, %1, %2;" : "=r"(r) : "r"(a), "r"(b)); return r;
}
__device__ __forceinline__ float ex2(float x) { float r; asm("ex2.approx.ftz.f32 %0, %1;" : "=f"(r) : "f"(x)); return r; }
__device__ __forceinline__ float rcp(float x) { float r; asm("rcp.approx.ftz.f32 %0, %1;" : "=f"(r) : "f"(x)); return r; }
__device__ __forceinline__ void ldsm4(uint32_t (&r)[4], uint32_t a) {
  asm volatile("ldmatrix.sync.aligned.m8n8.x4.shared.b16 {%0,%1,%2,%3}, [%4];"
               : "=r"(r[0]), "=r"(r[1]), "=r"(r[2]), "=r"(r[3]) : "r"(a) : "memory");
}
__device__ __forceinline__ void ldsm4t(uint32_t (&r)[4], uint32_t a) {
  asm volatile("ldmatrix.sync.aligned.m8n8.x4.trans.shared.b16 {%0,%1,%2,%3}, [%4];"
               : "=r"(r[0]), "=r"(r[1]), "=r"(r[2]), "=r"(r[3]) : "r"(a) : "memory");
}
__device__ __forceinline__ void stsm4(uint32_t a, uint32_t r0, uint32_t r1, uint32_t r2, uint32_t r3) {
  asm volatile("stmatrix.sync.aligned.m8n8.x4.shared.b16 [%0], {%1,%2,%3,%4};"
               ::"r"(a), "r"(r0), "r"(r1), "r"(r2), "r"(r3) : "memory");
}
__device__ __forceinline__ uint32_t lds32(uint32_t a) {
  uint32_t r; asm volatile("ld.shared.u32 %0, [%1];" : "=r"(r) : "r"(a) : "memory"); return r;
}
__device__ __forceinline__ uint32_t lds16(uint32_t a) {
  uint32_t r; asm volatile("{\n.reg .u16 h;\nld.shared.u16 h, [%1];\ncvt.u32.u16 %0, h;\n}\n" : "=r"(r) : "r"(a) : "memory"); return r;
}
__device__ __forceinline__ uint2 lds64(uint32_t a) {
  uint2 r; asm volatile("ld.shared.v2.u32 {%0,%1}, [%2];" : "=r"(r.x), "=r"(r.y) : "r"(a) : "memory"); return r;
}
__device__ __forceinline__ uint4 lds128(uint32_t a) {
  uint4 r;
  asm volatile("ld.shared.v4.u32 {%0,%1,%2,%3}, [%4];" : "=r"(r.x), "=r"(r.y), "=r"(r.z), "=r"(r.w) : "r"(a) : "memory");
  return r;
}
__device__ __forceinline__ void sts32(uint32_t a, uint32_t v) { asm volatile("st.shared.u32 [%0], %1;" ::"r"(a), "r"(v) : "memory"); }
__device__ __forceinline__ void sts16(uint32_t a, uint32_t v) {
  asm volatile("{\n.reg .u16 h;\ncvt.u16.u32 h, %1;\nst.shared.u16 [%0], h;\n}\n" ::"r"(a), "r"(v) : "memory");
}
__device__ __forceinline__ void sts64(uint32_t a, uint32_t x, uint32_t y) {
  asm volatile("st.shared.v2.u32 [%0], {%1,%2};" ::"r"(a), "r"(x), "r"(y) : "memory");
}
__device__ __forceinline__ void sts128(uint32_t a, uint32_t x, uint32_t y, uint32_t z, uint32_t w) {
  asm volatile("st.shared.v4.u32 [%0], {%1,%2,%3,%4};" ::"r"(a), "r"(x), "r"(y), "r"(z), "r"(w) : "memory");
}
__device__ __forceinline__ uint4 ld_x(const uint4* p) {
  uint4 r;
  asm volatile("{\n.reg .b128 t;\nld.relaxed.gpu.global.b128 t, [%4];\nmov.b128 {%0,%1,%2,%3}, t;\n}\n"
               : "=r"(r.x), "=r"(r.y), "=r"(r.z), "=r"(r.w) : "l"(p) : "memory");
  return r;
}
__device__ __forceinline__ uint32_t ld_x32(const uint32_t* p) {
  uint32_t r; asm volatile("ld.relaxed.gpu.global.u32 %0, [%1];" : "=r"(r) : "l"(p) : "memory"); return r;
}
__device__ __forceinline__ void st_x(uint4* p, uint32_t x, uint32_t y, uint32_t z, uint32_t w) {
  asm volatile("{\n.reg .b128 t;\nmov.b128 t, {%1,%2,%3,%4};\nst.relaxed.gpu.global.b128 [%0], t;\n}\n"
               ::"l"(p), "r"(x), "r"(y), "r"(z), "r"(w) : "memory");
}
__device__ __forceinline__ void st_x_p(int p, uint4* a, uint32_t x, uint32_t y, uint32_t z, uint32_t w) {
  asm volatile("{\n.reg .b128 t;\n.reg .pred q;\nsetp.ne.b32 q, %5, 0;\nmov.b128 t, {%1,%2,%3,%4};\n@q st.relaxed.gpu.global.b128 [%0], t;\n}\n"
               ::"l"(a), "r"(x), "r"(y), "r"(z), "r"(w), "r"(p) : "memory");
}
__device__ __forceinline__ void sts64_p(int p, uint32_t a, uint32_t x, uint32_t y) {
  asm volatile("{\n.reg .pred q;\nsetp.ne.b32 q, %3, 0;\n@q st.shared.v2.u32 [%0], {%1,%2};\n}\n" ::"r"(a), "r"(x), "r"(y), "r"(p) : "memory");
}
__device__ __forceinline__ void st_x32(uint32_t* p, uint32_t x) {
  asm volatile("st.relaxed.gpu.global.u32 [%0], %1;" ::"l"(p), "r"(x) : "memory");
}
__device__ __forceinline__ uint32_t nz(uint32_t w) { return max(w, 1u); }
__device__ __forceinline__ uint32_t fu(float x) { return __float_as_uint(x); }
__device__ __forceinline__ float uf(uint32_t x) { return __uint_as_float(x); }

__device__ __forceinline__ void wgmma_ss_n96(float (&d)[48], uint64_t da, uint64_t db, int sc) {
  asm volatile("{\n.reg .pred p;\nsetp.ne.b32 p, %50, 0;\n"
      "wgmma.mma_async.sync.aligned.m64n96k16.f32.bf16.bf16 "
      "{%0,%1,%2,%3,%4,%5,%6,%7,%8,%9,%10,%11,%12,%13,%14,%15,%16,%17,%18,%19,%20,%21,%22,%23,%24,%25,%26,%27,%28,%29,%30,%31,%32,%33,%34,%35,%36,%37,%38,%39,%40,%41,%42,%43,%44,%45,%46,%47}, "
      "%48, %49, p, 1, 1, 0, 1;\n}\n"
      : "+f"(d[0]), "+f"(d[1]), "+f"(d[2]), "+f"(d[3]), "+f"(d[4]), "+f"(d[5]), "+f"(d[6]), "+f"(d[7]),
        "+f"(d[8]), "+f"(d[9]), "+f"(d[10]), "+f"(d[11]), "+f"(d[12]), "+f"(d[13]), "+f"(d[14]), "+f"(d[15]),
        "+f"(d[16]), "+f"(d[17]), "+f"(d[18]), "+f"(d[19]), "+f"(d[20]), "+f"(d[21]), "+f"(d[22]), "+f"(d[23]),
        "+f"(d[24]), "+f"(d[25]), "+f"(d[26]), "+f"(d[27]), "+f"(d[28]), "+f"(d[29]), "+f"(d[30]), "+f"(d[31]),
        "+f"(d[32]), "+f"(d[33]), "+f"(d[34]), "+f"(d[35]), "+f"(d[36]), "+f"(d[37]), "+f"(d[38]), "+f"(d[39]),
        "+f"(d[40]), "+f"(d[41]), "+f"(d[42]), "+f"(d[43]), "+f"(d[44]), "+f"(d[45]), "+f"(d[46]), "+f"(d[47])
      : "l"(da), "l"(db), "r"(sc));
}

__device__ __forceinline__ void wgmma_ss_n128(float (&d)[64], uint64_t da, uint64_t db, int sc) {
  asm volatile("{\n.reg .pred p;\nsetp.ne.b32 p, %66, 0;\n"
      "wgmma.mma_async.sync.aligned.m64n128k16.f32.bf16.bf16 "
      "{%0,%1,%2,%3,%4,%5,%6,%7,%8,%9,%10,%11,%12,%13,%14,%15,%16,%17,%18,%19,%20,%21,%22,%23,%24,%25,%26,%27,%28,%29,%30,%31,%32,%33,%34,%35,%36,%37,%38,%39,%40,%41,%42,%43,%44,%45,%46,%47,%48,%49,%50,%51,%52,%53,%54,%55,%56,%57,%58,%59,%60,%61,%62,%63}, "
      "%64, %65, p, 1, 1, 0, 1;\n}\n"
      : "+f"(d[0]), "+f"(d[1]), "+f"(d[2]), "+f"(d[3]), "+f"(d[4]), "+f"(d[5]), "+f"(d[6]), "+f"(d[7]),
        "+f"(d[8]), "+f"(d[9]), "+f"(d[10]), "+f"(d[11]), "+f"(d[12]), "+f"(d[13]), "+f"(d[14]), "+f"(d[15]),
        "+f"(d[16]), "+f"(d[17]), "+f"(d[18]), "+f"(d[19]), "+f"(d[20]), "+f"(d[21]), "+f"(d[22]), "+f"(d[23]),
        "+f"(d[24]), "+f"(d[25]), "+f"(d[26]), "+f"(d[27]), "+f"(d[28]), "+f"(d[29]), "+f"(d[30]), "+f"(d[31]),
        "+f"(d[32]), "+f"(d[33]), "+f"(d[34]), "+f"(d[35]), "+f"(d[36]), "+f"(d[37]), "+f"(d[38]), "+f"(d[39]),
        "+f"(d[40]), "+f"(d[41]), "+f"(d[42]), "+f"(d[43]), "+f"(d[44]), "+f"(d[45]), "+f"(d[46]), "+f"(d[47]),
        "+f"(d[48]), "+f"(d[49]), "+f"(d[50]), "+f"(d[51]), "+f"(d[52]), "+f"(d[53]), "+f"(d[54]), "+f"(d[55]),
        "+f"(d[56]), "+f"(d[57]), "+f"(d[58]), "+f"(d[59]), "+f"(d[60]), "+f"(d[61]), "+f"(d[62]), "+f"(d[63])
      : "l"(da), "l"(db), "r"(sc));
}

__device__ __forceinline__ void wgmma_ss_n40(float (&d)[20], uint64_t da, uint64_t db, int sc) {
  asm volatile("{\n.reg .pred p;\nsetp.ne.b32 p, %22, 0;\n"
      "wgmma.mma_async.sync.aligned.m64n40k16.f32.bf16.bf16 "
      "{%0,%1,%2,%3,%4,%5,%6,%7,%8,%9,%10,%11,%12,%13,%14,%15,%16,%17,%18,%19}, "
      "%20, %21, p, 1, 1, 1, 1;\n}\n"
      : "+f"(d[0]), "+f"(d[1]), "+f"(d[2]), "+f"(d[3]), "+f"(d[4]), "+f"(d[5]), "+f"(d[6]), "+f"(d[7]),
        "+f"(d[8]), "+f"(d[9]), "+f"(d[10]), "+f"(d[11]), "+f"(d[12]), "+f"(d[13]), "+f"(d[14]), "+f"(d[15]),
        "+f"(d[16]), "+f"(d[17]), "+f"(d[18]), "+f"(d[19])
      : "l"(da), "l"(db), "r"(sc));
}

__device__ __forceinline__ void wgmma_rs_n8(float (&d)[4], const uint4& a, uint64_t db, int sc) {
  asm volatile("{\n.reg .pred p;\nsetp.ne.b32 p, %9, 0;\n"
      "wgmma.mma_async.sync.aligned.m64n8k16.f32.bf16.bf16 "
      "{%0,%1,%2,%3}, "
      "{%4,%5,%6,%7}, %8, p, 1, 1, 1;\n}\n"
      : "+f"(d[0]), "+f"(d[1]), "+f"(d[2]), "+f"(d[3])
      : "r"(a.x), "r"(a.y), "r"(a.z), "r"(a.w), "l"(db), "r"(sc));
}

__device__ __forceinline__ void wgmma_rs_n16(float (&d)[8], const uint4& a, uint64_t db, int sc) {
  asm volatile("{\n.reg .pred p;\nsetp.ne.b32 p, %13, 0;\n"
      "wgmma.mma_async.sync.aligned.m64n16k16.f32.bf16.bf16 "
      "{%0,%1,%2,%3,%4,%5,%6,%7}, "
      "{%8,%9,%10,%11}, %12, p, 1, 1, 1;\n}\n"
      : "+f"(d[0]), "+f"(d[1]), "+f"(d[2]), "+f"(d[3]), "+f"(d[4]), "+f"(d[5]), "+f"(d[6]), "+f"(d[7])
      : "r"(a.x), "r"(a.y), "r"(a.z), "r"(a.w), "l"(db), "r"(sc));
}

__device__ __forceinline__ void wgmma_rs_n24(float (&d)[12], const uint4& a, uint64_t db, int sc) {
  asm volatile("{\n.reg .pred p;\nsetp.ne.b32 p, %17, 0;\n"
      "wgmma.mma_async.sync.aligned.m64n24k16.f32.bf16.bf16 "
      "{%0,%1,%2,%3,%4,%5,%6,%7,%8,%9,%10,%11}, "
      "{%12,%13,%14,%15}, %16, p, 1, 1, 1;\n}\n"
      : "+f"(d[0]), "+f"(d[1]), "+f"(d[2]), "+f"(d[3]), "+f"(d[4]), "+f"(d[5]), "+f"(d[6]), "+f"(d[7]),
        "+f"(d[8]), "+f"(d[9]), "+f"(d[10]), "+f"(d[11])
      : "r"(a.x), "r"(a.y), "r"(a.z), "r"(a.w), "l"(db), "r"(sc));
}

struct Params {
  const __nv_bfloat16 *logA, *Aim, *Cre, *Cim, *logdt, *Dskip, *x, *wphi, *wo;
  __nv_bfloat16* out;
  uint4* xs;
  long long* ts;
};

__device__ __forceinline__ uint4 tr_row(const uint4 (&v)[8], int i) {
  uint32_t o[4];
#pragma unroll
  for (int m = 0; m < 4; m++) {
    const uint4 &ra = v[2 * m], &rb = v[2 * m + 1];
    const int k = i >> 1;
    const uint32_t xa = k == 0 ? ra.x : k == 1 ? ra.y : k == 2 ? ra.z : ra.w;
    const uint32_t xb = k == 0 ? rb.x : k == 1 ? rb.y : k == 2 ? rb.z : rb.w;
    o[m] = __byte_perm(xa, xb, (i & 1) ? 0x7632 : 0x5410);
  }
  return make_uint4(o[0], o[1], o[2], o[3]);
}

struct cpx { float r, i; };
__device__ __forceinline__ cpx csq(cpx a) { return {a.r * a.r - a.i * a.i, 2.f * (a.r * a.i)}; }
__device__ __forceinline__ cpx polar(float e, float t) {
  const float m = ex2(e);
  return {m * __cosf(t), m * __sinf(t)};
}

struct KgenRaw { unsigned short la, ai, cr, ci, ldt; };
__device__ __forceinline__ KgenRaw kgen_load(const Params& P, int d, int unit, int lane) {
  const int o = d * 128 + unit * 32 + lane;
  return {__ldg((const unsigned short*)P.logA + o), __ldg((const unsigned short*)P.Aim + o), __ldg((const unsigned short*)P.Cre + o),
          __ldg((const unsigned short*)P.Cim + o), __ldg((const unsigned short*)P.logdt + d)};
}
struct hmul { __half2 a, b; };
__device__ __forceinline__ hmul mk_mul(cpx w) {
  uint32_t b;
  asm("{\n.reg .f32 n;\nneg.ftz.f32 n, %1;\ncvt.rn.f16x2.f32 %0, %2, n;\n}\n" : "=r"(b) : "f"(w.i), "f"(w.r));
  return {__floats2half2_rn(w.r, w.i), *(const __half2*)&b};
}
__device__ __forceinline__ __half2 hcm(__half2 z, const hmul& w) { return __hfma2(__high2half2(z), w.b, __hmul2(__low2half2(z), w.a)); }
__device__ __forceinline__ uint32_t hu(__half2 v) { return *(const uint32_t*)&v; }

struct KgenAddr { uint32_t sa, sb, lb, lc, la; };
__device__ __forceinline__ KgenAddr kgen_addr(int lane, uint32_t buf) {
  KgenAddr a;
  a.sa = buf + (lane & 7) * 128 + ((((lane >> 3) ^ lane) & 7) << 4);
  a.lb = buf + (lane >> 3) * 128 + (((lane ^ (lane >> 3)) & 7) << 4);
  a.la = buf + ((lane >> 3) & 1) * 1024 + (lane >> 4) * 128 + (((lane ^ (lane >> 4)) & 7) << 4);
  a.sb = a.sa ^ 64; a.lc = a.lb ^ 64;
  asm volatile("" : "+r"(a.sa), "+r"(a.sb), "+r"(a.lb), "+r"(a.lc), "+r"(a.la));
  return a;
}
__device__ __forceinline__ void kgen_unit(const KgenRaw& r, const KgenAddr& ad, uint32_t zero, float (&k)[5][4], float& k2048, float& sc) {
  const float dt = bf_round(expf(bf_lo(r.ldt)));
  const float a2 = bf_round(ex2(bf_lo(r.la) * 1.4426950408889634f)) * (dt * -1.4426950408889634f);
  const float f = bf_lo(r.ai) * dt;
  const float r128 = f * 20.371832715762604f;
  const uint32_t ex = min(max(__reduce_max_sync(0xffffffffu, max(r.cr & 0x7fffu, r.ci & 0x7fffu)) >> 7, 1u), 253u);
  const float cs = uf((254u - ex) << 23);
  sc = 2.f * dt * uf(ex << 23);
  const cpx C = {bf_lo(r.cr) * cs, -bf_lo(r.ci) * cs};
  auto put = [&](const __half2 (&v)[8], uint32_t off) {
    stsm4(ad.sa + off, hu(v[0]), hu(v[1]), hu(v[2]), hu(v[3]));
    stsm4(ad.sb + off, hu(v[4]), hu(v[5]), hu(v[6]), hu(v[7]));
  };
  uint32_t A[4][4], B[5][2][4];
  auto get = [&](int j, uint32_t off) {
    __syncwarp();
    ldsm4(B[j][0], ad.lb + off);
    ldsm4(B[j][1], ad.lc + 512 + off);
  };
  auto tile = [&](int j) {
    k[j][0] = k[j][1] = k[j][2] = k[j][3] = 0.f;
#pragma unroll
    for (int s = 0; s < 4; s++) mma_h(k[j], A[s], B[j][s >> 1][2 * (s & 1)], B[j][s >> 1][2 * (s & 1) + 1]);
  };
  auto after = [&](cpx v, uint32_t dep) { return cpx{uf(fu(v.r) ^ (dep & zero)), v.i}; };
  const cpx w1 = polar(a2, f), w128 = polar(a2 * 128.f, (r128 - rintf(r128)) * 6.283185307179586f);
  const cpx w2 = csq(w1), w4 = csq(w2);
  __half2 t0[8], t1[8], t2[8], t3[8], t4[8];
  const hmul m2 = mk_mul(w2), m4 = mk_mul(w4), m128 = mk_mul(w128);
  t0[0] = __floats2half2_rn(1.f, 0.f); t0[1] = __floats2half2_rn(w1.r, w1.i); t0[2] = m2.a; t0[4] = m4.a;
  t0[3] = hcm(t0[1], m2); t0[5] = hcm(t0[1], m4); t0[6] = hcm(t0[2], m4); t0[7] = hcm(t0[3], m4);
  put(t0, 0); get(0, 0);
  t1[0] = m128.a;
#pragma unroll
  for (int i = 1; i < 8; i++) t1[i] = hcm(t0[i], m128);
  put(t1, 1024); get(1, 1024);
  {
    cpx w8 = csq(after(w4, B[0][0][0]));
    w8.i = -w8.i;
    const cpx w16 = csq(w8), w32 = csq(w16), w64 = csq(w32);
    const hmul m8 = mk_mul(w8), m16 = mk_mul(w16), m32 = mk_mul(w32), m64 = mk_mul(w64);
    __half2 a[8];
    a[0] = __floats2half2_rn(C.r, C.i); a[1] = hcm(a[0], m8);
    a[2] = hcm(a[0], m16); a[3] = hcm(a[1], m16);
#pragma unroll
    for (int i = 0; i < 4; i++) a[4 + i] = hcm(a[i], m32);
    put(a, 0);
#pragma unroll
    for (int i = 0; i < 8; i++) a[i] = hcm(a[i], m64);
    put(a, 1024);
    __syncwarp();
#pragma unroll
    for (int s = 0; s < 4; s++) ldsm4(A[s], (ad.la ^ (s << 5)) + s * 256);
  }
  const cpx w256 = csq(after(w128, B[1][0][0]));
  const hmul m256 = mk_mul(w256);
  t2[0] = m256.a;
#pragma unroll
  for (int i = 1; i < 8; i++) t2[i] = hcm((i & 1) ? t1[i & 6] : t0[i & 6], m256);
  put(t2, 0); get(2, 0);
  tile(0); tile(1);
  const cpx w512 = csq(after(w256, A[0][0]));
  const hmul m512 = mk_mul(w512);
  t3[0] = m512.a;
#pragma unroll
  for (int i = 1; i < 8; i++) t3[i] = hcm((i & 2) ? t2[i & 5] : ((i & 1) ? t1[i & 4] : t0[i & 4]), m512);
  put(t3, 1024); get(3, 1024);
  tile(2);
  const cpx w1024 = csq(after(w512, B[2][0][0])), we = csq(w1024);
  const hmul m1024 = mk_mul(w1024);
  t4[0] = m1024.a;
#pragma unroll
  for (int i = 1; i < 8; i++) t4[i] = hcm((i & 4) ? t3[i & 3] : ((i & 2) ? t2[i & 1] : t1[0]), m1024);
  put(t4, 0); get(4, 0);
  tile(3); tile(4);
  k2048 = (C.r * we.r + C.i * we.i) * sc;
}

__device__ __forceinline__ void build_tables(uint32_t tb, int lane, float (&k)[5][4], float k2048) {
  const int g = lane >> 2, c = lane & 3;
  const uint32_t kc = tb + T_KC + 16;
  {
    const uint32_t a0 = kc + 16 * g + 4 * c, a2 = kc + 2 * (256 + 4 * g + c);
    const uint32_t a3 = kc + 2 * (384 + 2 * g + 64 * (c & 1) + (c >> 1)), a4 = kc + 2 * (512 + g + 32 * c);
#pragma unroll
    for (int r = 0; r < 2; r++) {
      sts32(a0 + 128 * r, pack_bf(k[0][2 * r], k[0][2 * r + 1]));
      sts32(a0 + 128 * r + 256, pack_bf(k[1][2 * r], k[1][2 * r + 1]));
      const uint32_t w2 = pack_bf(k[2][2 * r], k[2][2 * r + 1]);
      const uint32_t w3 = pack_bf(k[3][2 * r], k[3][2 * r + 1]);
      const uint32_t w4 = pack_bf(k[4][2 * r], k[4][2 * r + 1]);
      sts16(a2 + 64 * r, w2); sts16(a2 + 64 * r + 128, w2 >> 16);
      sts16(a3 + 32 * r, w3); sts16(a3 + 32 * r + 64, w3 >> 16);
      sts16(a4 + 16 * r, w4); sts16(a4 + 16 * r + 32, w4 >> 16);
    }
  }
  if (lane == 0) { sts16(kc + 2 * 640, pack_bf(k2048, 0.f)); sts32(kc - 4, 0); }
  __syncwarp();
  const uint32_t td = tb + T_D + 32;
#pragma unroll
  for (int hf = 0; hf < 2; hf++) {
    const uint2 v = lds64(kc + 256 * hf + 8 * lane);
    const uint32_t pv = lds32(kc + 256 * hf + 8 * lane - 4);
    sts128(td + 512 * hf + 16 * lane, __byte_perm(v.x, pv, 0x7610), __byte_perm(v.x, v.x, 0x1032), __byte_perm(v.y, v.x, 0x7610),
           __byte_perm(v.y, v.y, 0x1032));
  }
#pragma unroll
  for (int hf = 0; hf < 2; hf++) {
    const uint32_t v = lds32(kc + 512 + 128 * hf + 4 * lane), nx = lds32(kc + 516 + 128 * hf + 4 * lane);
    uint32_t w0 = __byte_perm(v, v, 0x1010);
    const uint32_t w1 = w0;
    if (hf == 0) { const uint32_t pv = lds32(kc + 508); if (lane == 0) w0 = __byte_perm(v, pv, 0x7610); }
    sts128(td + 1024 + 512 * hf + 16 * lane, w0, w1, __byte_perm(v, v, 0x1032), __byte_perm(nx, v, 0x7610));
  }
  {
    const uint32_t kk = lds16(kc + 2 * 384);
    const uint32_t w = lane < 3 ? (kk | (kk << 16)) : (lane == 3 ? (kk << 16) : 0u);
    if (lane < 24) sts32(td + 4 * (lane < 16 ? 512 + lane : lane - 24), w);
    const uint32_t lo_ = lds16(kc + 2 * 511), le_ = lds16(kc + 2 * 512);
    const uint32_t ja = tb + T_5 + (lane < 16 ? 4 * lane : 256 + 4 * lane);
    sts32(ja, lane == 16 ? (le_ << 16) : 0u);
    sts32(ja + 384, lane == 16 ? (lo_ << 16) : 0u);
    sts32(tb + (lane < 16 ? T_7 : T_9 - 64) + 4 * lane, 0u);
  }
#pragma unroll
  for (int s = 0; s < 2; s++) {
    const uint32_t b = kc + 2 * (s ? 512 : 384) + 8 * lane;
    const uint2 v = lds64(b);
    uint32_t em = lds16(b - 2), e0 = v.x;
    const uint32_t e4 = lds16(b + 8);
    if (lane == 0) { em = 0; e0 = 0; }
    sts64(tb + (s ? T_7 : T_3) + 64 + 8 * lane, __byte_perm(v.x, em, 0x5432), __byte_perm(v.y, v.x, 0x7632));
    sts64(tb + (s ? T_9 : T_5) + 64 + 8 * lane, __byte_perm(v.y, e0, 0x5410), __byte_perm(e4, v.y, 0x5410));
  }
  __syncwarp();
}

__device__ __forceinline__ uint32_t box2w(int lo, int n, int o) {
  return ((unsigned)(o - lo) < (unsigned)n ? 0x3F80u : 0u) | ((unsigned)(o + 1 - lo) < (unsigned)n ? 0x3F800000u : 0u);
}

__device__ __forceinline__ void conv_channel(uint32_t ub, uint32_t tb, int lane, uint4* ydst) {
  const int g = lane >> 2, c = lane & 3, x = g - 2 * c;
  const int mi = lane >> 3;
  const uint32_t qa = ub + U_PAD + 16 * (lane & 7) + ((mi == 0 || mi == 3) ? U_ODD : 0) - (mi == 0 ? 16 : 0);
  const uint32_t hb = ub + U_PAD + (mi & 1) * U_ODD + 16 * ((lane >> 4) + (lane & 7)) - 16;
  const uint32_t kv = lds16(tb + T_KC + 16 + 2 * 512);
  const int oh = c < 2 ? 8 + 2 * c : 2 * c - 8, og = c < 3 ? 2 * c : -10;
  uint32_t bx[4] = {box2w(g - 4, 9, 2 * c), box2w(g - 3, 7, 2 * c), box2w(g - 4, 9, oh), box2w(g - 3, 7, oh)};
  uint32_t by[4] = {box2w(g - 10, 5, 2 * c - 8), box2w(g - 5, 3, 2 * c - 8), box2w(g - 10, 5, og), box2w(g - 5, 3, og)};
  uint32_t lb0 = ((unsigned)(x + 5) < 2u ? kv : 0u) | ((unsigned)(x + 4) < 2u ? kv << 16 : 0u);
  uint32_t lb1 = ((unsigned)(x - 3) < 2u ? kv : 0u) | ((unsigned)(x - 4) < 2u ? kv << 16 : 0u);
  const int q0 = g - 1, q1 = c < 3 ? g : g - 2;
  uint32_t y0a = ub + U_PAD + (q0 & 1) * U_ODD + 16 * (q0 >> 1) + 4 * c;
  uint32_t y1a = ub + U_PAD + (q1 & 1) * U_ODD + 16 * (q1 >> 1) + 4 * c;
#pragma unroll
  for (int i = 0; i < 4; i++) asm volatile("" : "+r"(bx[i]), "+r"(by[i]));
  asm volatile("" : "+r"(lb0), "+r"(lb1), "+r"(y0a), "+r"(y1a));
  mbar_wait(BAR(MB_UFULL));
  mbar_wait(BAR(MB_EMPTY + 15));
  TS(36);
  float acc[16][4];
  {
    uint32_t z09[8], z07[8], zm9[8], zm7[8];
#pragma unroll
    for (int i = 0; i < 8; i++) {
      uint32_t h[4];
      ldsm4(h, hb + 128 * i);
      float y0, y1, y2, y3, w0, w1, w2, w3;
      mma0(y0, y1, y2, y3, bx[0], bx[1], bx[2], bx[3], h[2], c < 2 ? h[3] : h[1]);
      mma0(w0, w1, w2, w3, bx[0], bx[1], bx[2], bx[3], h[1], c < 2 ? h[2] : h[0]);
      z09[i] = pack_bf(y0, y1); z07[i] = pack_bf(y2, y3);
      zm9[i] = pack_bf(w0, w1); zm7[i] = pack_bf(w2, w3);
    }
  uint32_t f3[3][4][4];
  {
    const uint32_t fa = tb + T_7 + 4 * (16 + x);
#pragma unroll
    for (int tt = 0; tt < 3; tt++)
#pragma unroll
      for (int D = 0; D < 4; D++) {
        const uint32_t a = fa + (tt == 0 ? 316 : (tt == 1 ? 320 : 0)) + 64 * D;
        f3[tt][D][0] = lds32(a); f3[tt][D][1] = lds32(a + 32); f3[tt][D][2] = lds32(a - 32); f3[tt][D][3] = lds32(a);
      }
  }
    float a[4][2][4];
#pragma unroll
    for (int kap = 0; kap < 4; kap++)
#pragma unroll
      for (int sg = 0; sg < 2; sg++)
#pragma unroll
        for (int bk = 3; bk >= kap; bk--) {
          const uint32_t(&q0_)[4] = f3[sg ? 2 : 0][bk - kap];
          const uint32_t(&q1_)[4] = f3[sg ? 2 : 1][bk - kap];
          float(&a0)[4] = a[bk][0];
          float(&a1)[4] = a[bk][1];
          if (sg == 0 && kap == 0) {
            mma0(a0[0], a0[1], a0[2], a0[3], q0_[0], q0_[1], q0_[2], q0_[3], z09[0], z09[1]);
            mma0(a1[0], a1[1], a1[2], a1[3], q1_[0], q1_[1], q1_[2], q1_[3], zm9[0], zm9[1]);
          } else {
            mma(a0[0], a0[1], a0[2], a0[3], q0_[0], q0_[1], q0_[2], q0_[3], sg ? zm7[2 * kap] : z09[2 * kap], sg ? zm7[2 * kap + 1] : z09[2 * kap + 1]);
            mma(a1[0], a1[1], a1[2], a1[3], q1_[0], q1_[1], q1_[2], q1_[3], sg ? z07[2 * kap] : zm9[2 * kap], sg ? z07[2 * kap + 1] : zm9[2 * kap + 1]);
          }
        }
    SPLIT();
#pragma unroll
    for (int i = 0; i < 8; i++) {
      uint32_t h[4];
      ldsm4(h, qa + 128 * i);
      const float ci[4] = {a[i >> 1][0][2 * (i & 1)], a[i >> 1][0][2 * (i & 1) + 1], a[i >> 1][1][2 * (i & 1)], a[i >> 1][1][2 * (i & 1) + 1]};
      mmac(acc[8 + i], h[0], h[1], h[2], h[3], lb0, lb1, ci);
    }
  }
  TS(44);
  {
    uint2 a5[10], a3[10];
    const uint32_t aa = tb + T_5 + 4 * (8 + 2 * g - 2 * c);
#pragma unroll
    for (int m = 0; m < 10; m++) { a5[m] = lds64(aa + 32 * m); a3[m] = lds64(aa + 384 + 32 * m); }
    uint32_t x5[12][2], x3[12][2];
    auto ygen = [&](int kap) {
#pragma unroll
      for (int hh = 0; hh < 2; hh++) {
        float y0, y1, y2, y3;
        mma0(y0, y1, y2, y3, by[0], by[1], by[2], by[3], lds32(y0a + 128 * kap + 64 * hh), lds32(y1a + 128 * kap + 64 * hh));
        x5[kap][hh] = pack_bf(y0, y1);
        x3[kap][hh] = pack_bf(y2, y3);
      }
    };
    ygen(11); ygen(10); ygen(9); ygen(8);
#pragma unroll
    for (int kap = 11; kap >= 0; kap--) {
      if (kap >= 4) ygen(kap - 4);
#pragma unroll
      for (int sg = 0; sg < 2; sg++)
#pragma unroll
        for (int i = 4; i >= 0; i--) {
          const int be = kap + 4 + i;
          if (be <= 15) {
            const uint2 &hi = sg ? a3[2 * i + 1] : a5[2 * i + 1], &lo = sg ? a3[2 * i] : a5[2 * i];
            const uint32_t b0 = sg ? x3[kap][0] : x5[kap][0], b1 = sg ? x3[kap][1] : x5[kap][1];
            if (be < 8 && i == 0 && sg == 0) mma0(acc[be][0], acc[be][1], acc[be][2], acc[be][3], hi.x, hi.y, lo.x, lo.y, b0, b1);
            else mma(acc[be][0], acc[be][1], acc[be][2], acc[be][3], hi.x, hi.y, lo.x, lo.y, b0, b1);
          }
        }
    }
  }
  TS(45);
  {
    const uint32_t st = tb + T_ST + lane * 8;
#pragma unroll
    for (int be = 4; be < 12; be++) sts64(st + 256 * be, pack_bf(acc[be][0], acc[be][1]), pack_bf(acc[be][2], acc[be][3]));
    SPLIT();
    uint32_t F[66], qd[8][4];
    const uint32_t fa = tb + T_D + 32 + 4 * x;
#pragma unroll
    for (int i = 0; i < 32; i++) {
      const int s = 120 - (i >> 2) - 8 * (i & 3);
      uint32_t(&q)[4] = qd[i & 7];
      ldsm4(q, qa + 16 * s);
      const int m = 16 * (i & 3) + 2 * (i >> 2);
      F[m] = lds32(fa + 32 * m); F[m + 1] = lds32(fa + 32 * m + 32);
#pragma unroll
      for (int be = 15; be >= 12; be--) {
        const int de = 8 * be - s;
        float(&a)[4] = (be >= 14 && !(i & 1)) ? acc[be - 4] : acc[be];
        if (de >= 0 && be >= 14 && i == 2 * (15 - be)) mma0(a[0], a[1], a[2], a[3], q[0], q[1], q[2], q[3], F[2 * de + 1], F[2 * de]);
        else if (de >= 0) mma(a[0], a[1], a[2], a[3], q[0], q[1], q[2], q[3], F[2 * de + 1], F[2 * de]);
      }
    }
#pragma unroll
    for (int i = 0; i < 8; i++) acc[14 + (i >> 2)][i & 3] += acc[10 + (i >> 2)][i & 3];
    F[64] = lds32(fa + 32 * 64); F[65] = lds32(fa + 32 * 65);
    uint32_t qp = qa + 128 * 11, sta = st + 256 * 10;
    uint4* yd = ydst + 7 * 32;
#pragma unroll
    for (int i = 0; i < 6; i++) ldsm4(qd[i], qp - 16 * i);
    uint2 sv = lds64(sta + 256);
    float ci[4] = {bf_lo(sv.x), bf_hi(sv.x), bf_lo(sv.y), bf_hi(sv.y)};
    float T[5][4];
#pragma unroll
    for (int i = 0; i < 16; i++) T[i >> 2][i & 3] = acc[12 + (i >> 2)][i & 3];
    nb_sync(NB_YZ, 160);
    TS(46);
#pragma unroll 1
    for (int bp = 5; bp >= 0; bp--) {
      uint32_t held[2];
#pragma unroll
      for (int o = 1; o >= 0; o--) {
#pragma unroll
        for (int k = 4; k >= 1; k--) mmac(T[k], qd[0][0], qd[0][1], qd[0][2], qd[0][3], F[16 * k + 1], F[16 * k], T[k - 1]);
        mmac(T[0], qd[0][0], qd[0][1], qd[0][2], qd[0][3], F[1], F[0], ci);
        ldsm4(qd[6], qp - 16 * 6);
        ldsm4(qd[7], qp - 16 * 7);
        sv = lds64(sta);
#pragma unroll
        for (int i = 1; i < 8; i++) {
#pragma unroll
          for (int k = 3; k >= 0; k--)
            mma(T[k][0], T[k][1], T[k][2], T[k][3], qd[i][0], qd[i][1], qd[i][2], qd[i][3], F[16 * k + 2 * i + 1], F[16 * k + 2 * i]);
          if (i < 7) ldsm4(qd[i - 1], qp - 128 - 16 * (i - 1));
          if (i == 2) {
            const uint32_t w0 = pack_bf(T[4][0], T[4][1]), w1 = pack_bf(T[4][2], T[4][3]);
            if (o) { held[0] = w0; held[1] = w1; }
            else st_x(yd, nz(w0), w1, held[0], held[1]);
          }
          if (i == 4) {
            if (2 * bp + o <= 4) sv = make_uint2(0, 0);
            ci[0] = bf_lo(sv.x); ci[1] = bf_hi(sv.x); ci[2] = bf_lo(sv.y); ci[3] = bf_hi(sv.y);
          }
        }
        qp -= 128; sta -= 256;
      }
      yd -= 32;
    }
#pragma unroll
    for (int B = 1; B >= 0; B--)
      st_x(ydst + B * 32, nz(pack_bf(T[2 * B][0], T[2 * B][1])), pack_bf(T[2 * B][2], T[2 * B][3]),
           pack_bf(T[2 * B + 1][0], T[2 * B + 1][1]), pack_bf(T[2 * B + 1][2], T[2 * B + 1][3]));
  }
}

__device__ __forceinline__ void dual_exp(const uint32_t* w, uint32_t* e) {
  const float L = 1.44268798828125f;
  uint32_t mx = bmax2(bmax2(w[0], w[1]), bmax2(w[2], w[3]));
  uint32_t mn = bmin2(bmin2(w[0], w[1]), bmin2(w[2], w[3]));
  mx = bmax2(mx, __shfl_xor_sync(0xffffffffu, mx, 1));
  mn = bmin2(mn, __shfl_xor_sync(0xffffffffu, mn, 1));
  mx = bmax2(mx, __shfl_xor_sync(0xffffffffu, mx, 2));
  mn = bmin2(mn, __shfl_xor_sync(0xffffffffu, mn, 2));
  const float mx0 = bf_lo(mx) * -L, mx1 = bf_hi(mx) * -L, mn0 = bf_lo(mn) * L, mn1 = bf_hi(mn) * L;
#pragma unroll
  for (int i = 0; i < 2; i++) {
    const float a0 = bf_lo(w[2 * i]), a1 = bf_hi(w[2 * i]), b0 = bf_lo(w[2 * i + 1]), b1 = bf_hi(w[2 * i + 1]);
    e[2 * i] = pack_bf(ex2(fmaf(a0, L, mx0)), ex2(fmaf(b0, L, mx0)));
    e[2 * i + 1] = pack_bf(ex2(fmaf(a1, L, mx1)), ex2(fmaf(b1, L, mx1)));
    e[4 + 2 * i] = pack_bf(ex2(fmaf(a0, -L, mn0)), ex2(fmaf(b0, -L, mn0)));
    e[5 + 2 * i] = pack_bf(ex2(fmaf(a1, -L, mn1)), ex2(fmaf(b1, -L, mn1)));
  }
}
__device__ __forceinline__ void normalise(uint32_t* e, const float (&s)[4]) {
  const uint32_t r = pack_bf(rcp(s[0]), rcp(s[2]));
  const __nv_bfloat162 rr = *(const __nv_bfloat162*)&r;
#pragma unroll
  for (int i = 0; i < 4; i++) {
    const __nv_bfloat162 v = __hmul2(*(const __nv_bfloat162*)&e[i], (i & 1) ? __high2bfloat162(rr) : __low2bfloat162(rr));
    e[i] = *(const uint32_t*)&v;
  }
}
__host__ __device__ constexpr uint64_t qdesc(uint32_t addr) { return mkdesc(addr, 128, 256, 0); }

__global__ void __launch_bounds__(NTHREADS, 1)
fused_kernel(const Params P, const __grid_constant__ CUtensorMap mx, const __grid_constant__ CUtensorMap mw,
             const __grid_constant__ CUtensorMap mo, const __grid_constant__ CUtensorMap mu,
             const __grid_constant__ CUtensorMap mout, const __grid_constant__ CUtensorMap mw4) {
  constexpr uint32_t sb = SB;
  const int tid = threadIdx.x, lane = tid & 31;
  const int warp = __shfl_sync(0xffffffffu, tid >> 5, 0);
  const int b = blockIdx.x, oct = b >> 3, i8 = b & 7;
  const int rt = oct < 8 ? oct : 15 - oct;
  const int hp = (oct >> 3) * 8 + i8;

  const int wg = warp >> 2, w = warp & 3;
  const int d = b * 4 + ((tid >> 5) & 3);
  if (tid < 384) {
    asm volatile("prefetch.tensormap [%0];" ::"l"(&mu) : "memory");
    asm volatile("prefetch.tensormap [%0];" ::"l"(&mw) : "memory");
    asm volatile("prefetch.tensormap [%0];" ::"l"(&mx) : "memory");
    asm volatile("prefetch.tensormap [%0];" ::"l"(&mw4) : "memory");
  }
  if (warp == 12) {
    if (lane == 0) {
#pragma unroll
      for (int i = 0; i < 9; i++) mbar_init(BAR(i), 1);
      asm volatile("fence.mbarrier_init.release.cluster;" ::: "memory");
    }
    __syncwarp();
    if (lane < 9) mbar_expect(BAR(0) + 8 * lane, lane == 5 ? 65536 : ((lane == 0 || lane > 5) ? 16384 : 28672));
    __syncwarp();
    e_tma3d(sb + OFF_W, &mw, BAR(MB_FULL), hp * 32, 0, 0);
    e_tma2d(sb + OFF_X + 3 * 16384, &mx, BAR(MB_FULL), 0, rt * 256);
    nb_arrive(NB_PROD, 192);
  } else if (warp == 13) {
    if (lane == 0) {
#pragma unroll
      for (int i = 9; i < 39; i++) mbar_init(BAR(i), i < MB_EMPTY ? 1 : (i < MB_AUX ? 4 : 8));
      asm volatile("fence.mbarrier_init.release.cluster;" ::: "memory");
    }
    __syncwarp();
    if (lane < 9) mbar_expect(BAR(MB_FULL + 8) + 8 * lane, lane < 8 ? 16384 : 131072);
    nb_arrive(NB_PROD, 192);
  }
  const KgenRaw raw = kgen_load(P, d, tid >> 7, lane);
  const unsigned short dsk = __ldg((const unsigned short*)P.Dskip + d);
  const uint32_t tb = sb + OFF_T + w * T_CH;
  const uint32_t kp = wg >= 2 ? sb + OFF_STG0 + 16384 + w * 2048 : ((tb + 127) & ~127u) + wg * 2048;
  const KgenAddr kad = kgen_addr(lane, wg == 3 ? sb + OFF_X + 32768 + w * 2048 : kp);
  if (wg == 1) nb_sync(NB_PROD, 192);
  if (warp == 12) {
#pragma unroll 1
    for (int kb = 1; kb < 4; kb++) {
      if (kb == U_AT) e_tma4d(sb + OFF_STG0, &mu, BAR(MB_URAW), i8 * 64, oct * 2);
      e_tma3d(sb + OFF_W + kb * 12288, &mw, BAR(MB_FULL) + 8 * kb, hp * 32, kb * 64, 0);
      e_tma2d(sb + OFF_X + (kb < 2 ? kb + 3 : kb - 2) * 16384, &mx, BAR(MB_FULL) + 8 * kb, kb * 64, rt * 256);
    }
    e_prefetch(P.x + (size_t)(rt * 256 + hp * 16) * 512, 16384);
    e_tma4d(sb + OFF_W + 4 * 12288, &mw4, BAR(MB_FULL + 4), hp * 32, 4);
    if (smem_u32(smem_raw) != SB) __trap();
    if (lane == 0) TS1(54);
  }
  float k[5][4], k2048, ksc;
  kgen_unit(raw, kad, blockIdx.y, k, k2048, ksc);
  TS(40 + wg);
  if ((fu(k[0][0]) & fu(k[1][0]) & fu(k[2][0]) & fu(k[3][0]) & fu(k[4][0])) == 0xffffffffu) sts32(kp, 0);
  if (wg == 3) {
    nb_sync(0, 512);
    if (warp == 12) {
      asm volatile("fence.proxy.async.shared::cta;" ::: "memory");
      e_tma2d(sb + OFF_X + 2 * 16384, &mx, BAR(MB_FULL + 4), 256, rt * 256);
    }
  } else if (wg) {
    nb_arrive(0, 512);
  }
  k2048 += __shfl_xor_sync(0xffffffffu, k2048, 16);
  k2048 += __shfl_xor_sync(0xffffffffu, k2048, 8);
  if (wg != 2) {
    uint32_t h[10];
#pragma unroll
    for (int j = 0; j < 10; j++) h[j] = hu(__floats2half2_rn(k[j >> 1][2 * (j & 1)], k[j >> 1][2 * (j & 1) + 1]));
    sts128(kp + lane * 16, h[0], h[1], h[2], h[3]);
    sts128(kp + 512 + lane * 16, h[4], h[5], h[6], h[7]);
    sts128(kp + 1024 + lane * 16, h[8], h[9], fu(k2048), fu(ksc));
  }
  if (wg == 0) { nb_arrive(NB_PREP, 512); nb_sync(0, 512); }
  else if (wg != 2) nb_arrive(NB_PREP, 512);
  else nb_sync(NB_PREP, 512);
  if (warp >= 12) {
    asm volatile("setmaxnreg.dec.sync.aligned.u32 32;");
    if (warp == 12) {
      uint32_t slot = sb + OFF_X + 3 * 16384;
#pragma unroll 1
      for (int n = 0; n < 11; n++) {
        mbar_spin(BAR(MB_EMPTY) + 8 * n);
        const int m = n + 5;
        e_tma2d(slot, &mx, BAR(MB_FULL) + 8 * m, (m & 7) * 64, rt * 256 + (m >> 3) * 128);
        slot = slot == sb + OFF_X + 4 * 16384 ? sb + OFF_X : slot + 16384;
        if (n == 7) {
          e_prefetch(P.wo + (size_t)b * 2048, 4096);
          asm volatile("prefetch.tensormap [%0];" ::"l"(&mo) : "memory");
          asm volatile("prefetch.tensormap [%0];" ::"l"(&mout) : "memory");
        }
      }
#pragma unroll 1
      for (int i = 0; i < 8; i++) {
        mbar_wait(BAR(MB_EMPTY + 10) + 8 * ((0x54332100u >> (4 * i)) & 7));
        const int w0 = (0x54736210u >> (4 * i)) & 7;
        e_tma3d(sb + OFF_W + w0 * 16384, &mo, BAR(MB_WO), 0, w0 * 64, (hp & 3) * 2);
      }
    } else {
      if (warp == 15) {
        const uint4 v0 = __ldg((const uint4*)P.wphi + hp * 64 + lane), v1 = __ldg((const uint4*)P.wphi + hp * 64 + 32 + lane);
        sts128(sb + OFF_PHI + (lane & 1) * 256 + (lane >> 1) * 16, v0.x, v0.y, v0.z, v0.w);
        sts128(sb + OFF_PHI + 512 + (lane & 1) * 256 + (lane >> 1) * 16, v1.x, v1.y, v1.z, v1.w);
        const uint32_t one = (((lane >> 3) ^ (lane >> 4)) & 1) ? 0u : ((lane & 1) ? 0x3F800000u : 0x3F80u);
        const int q = (lane >> 1) & 3;
        sts128(sb + OFF_EYE + lane * 16, q == 0 ? one : 0u, q == 1 ? one : 0u, q == 2 ? one : 0u, q == 3 ? one : 0u);
        sts64(sb + OFF_ONE + lane * 8, 0x3F803F80u, 0x3F803F80u);
        asm volatile("fence.proxy.async.shared::cta;" ::: "memory");
        nb_arrive(NB_KREAD, 160);
      }
      uint32_t* cnt = (uint32_t*)(P.xs + X_CNT) + (warp == 13 ? i8 : (warp == 14 ? 8 + rt : 16 + oct)) * 32;
      const unsigned target = (ld_x32(cnt) & ~31u) + 32;
      if (warp != 14) {
        if (warp == 15) mbar_wait(BAR(MB_EMPTY + ZERO_STEP));
        uint4* pz = P.xs + (warp == 13 ? X_PART + (hp * 8 + rt) * 144 : X_Y + b * 1024) + lane;
#pragma unroll 1
        for (int i = (warp == 13 ? 144 : 1024) - lane; i > 0; i -= 32, pz += 32) st_x(pz, 0, 0, 0, 0);
        if (warp == 15) __syncwarp();
        else nb_sync(NB_INIT, 160);
        if (lane == 0) TS1(warp == 13 ? 49 : 52);
        if (lane == 0) asm volatile("red.release.gpu.global.add.u32 [%0], %1;" ::"l"(cnt), "r"(warp == 15 ? 4 : 2) : "memory");
        if (lane == 0) TS1(warp == 13 ? 50 : 53);
        if (warp == 13 && (lane & 1)) cnt += ((b >> 4) - i8) * 32;
      } else {
        nb_sync(NB_ODONE, 288);
        asm volatile("fence.proxy.async.shared::cta;" ::: "memory");
      }
      {
        unsigned v0 = ld_x32(cnt), v1, v2;
        __nanosleep(100);
        v1 = ld_x32(cnt);
#pragma unroll 1
        for (int i = 0; i < SPIN_MAX; i++) {
          __nanosleep(100);
          v2 = ld_x32(cnt);
          if (__all_sync(0xffffffffu, (int)(v0 - target) >= 0)) break;
          v0 = v1; v1 = v2;
        }
        asm volatile("fence.acq_rel.cta;" ::: "memory");
      }
      if (lane == 0) TS1(warp == 13 ? 51 : (warp == 14 ? 58 : 55));
      if (warp == 15) { nb_arrive(NB_YZ, 160); return; }
      asm volatile("fence.proxy.async.global;" ::: "memory");
      if (warp == 13) {
        mbar_wait(BAR(MB_EMPTY + 11));
        e_expect(BAR(MB_UFULL), 4 * U_CH);
        e_bulk(sb + OFF_U, P.xs + X_UT + b * (U_CH / 4), 4 * U_CH, BAR(MB_UFULL));
      } else {
        const uint4* src = P.xs + X_O + (rt * 4 + (hp >> 2)) * 4096;
        e_expect(BAR(MB_OA), 14336);
        e_bulk(sb + OFF_STG0, src + 3200, 14336, BAR(MB_OA));
        e_expect(BAR(MB_OC), 32768);
        e_bulk(sb + OFF_X + 32768, src, 32768, BAR(MB_OC));
        nb_sync(NB_BDONE, 288);
        asm volatile("fence.proxy.async.shared::cta;" ::: "memory");
        e_expect(BAR(MB_OB), 18432);
        e_bulk(sb + OFF_U, src + 2048, 18432, BAR(MB_OB));
      }
    }
    return;
  }

  const int t = tid & 127;
  const int g = lane >> 2, c = lane & 3;
  {
    if (wg == 2) {
      asm volatile("setmaxnreg.inc.sync.aligned.u32 160;");
#pragma unroll
      for (int j = 0; j < 5; j++) { k[j][0] *= ksc; k[j][1] *= ksc; k[j][2] *= ksc; k[j][3] *= ksc; }
#pragma unroll 1
      for (int q = 0; q < 3; q++) {
        const uint32_t src = (q == 2 ? kp : ((tb + 127) & ~127u) + q * 2048) + lane * 16;
        const uint4 v0 = lds128(src), v1 = lds128(src + 512), v2 = lds128(src + 1024);
        const uint32_t h[10] = {v0.x, v0.y, v0.z, v0.w, v1.x, v1.y, v1.z, v1.w, v2.x, v2.y};
#pragma unroll
        for (int j = 0; j < 10; j++) {
          const float2 f = __half22float2(*(const __half2*)&h[j]);
          k[j >> 1][2 * (j & 1)] = fmaf(f.x, uf(v2.w), k[j >> 1][2 * (j & 1)]);
          k[j >> 1][2 * (j & 1) + 1] = fmaf(f.y, uf(v2.w), k[j >> 1][2 * (j & 1) + 1]);
        }
        k2048 += uf(v2.z);
      }
#pragma unroll
      for (int o2 = 4; o2; o2 >>= 1) k2048 += __shfl_xor_sync(0xffffffffu, k2048, o2);
      if (lane == 0) k[0][0] += bf_lo(dsk);
      __syncwarp();
      if (lane == 0) mbar_arrive(BAR(MB_AUX));
      TS(34);
      build_tables(tb, lane, k, k2048);
      TS(35);
      uint4* const g_y = P.xs + X_Y;
      conv_channel(sb + OFF_U + w * U_CH, tb, lane, g_y + (size_t)d * 256 + lane);
      nb_arrive(NB_BDONE, 288);
      TS(37);
      const int lam = w * 8 + g;
      const uint4* src = g_y + (size_t)(oct * 32 + c * 8) * 256 + i8 * 32 + lam;
      uint4 v[8];
#pragma unroll 1
      for (int it = 0; it < SPIN_MAX; it++) {
        uint32_t m = 0xffffffffu;
#pragma unroll
        for (int i = 0; i < 8; i++) v[i] = ld_x(src + i * 256);
#pragma unroll
        for (int i = 0; i < 8; i++) m = min(m, v[i].x);
        if (__all_sync(0xffffffffu, m != 0)) break;
      }
      __nv_bfloat16* dst = P.out + (size_t)(i8 * 256 + (lam >> 2) * 16 + (lam & 3) * 2) * 1024 + 512 + oct * 32 + c * 8;
#pragma unroll
      for (int i = 0; i < 8; i++) *(uint4*)(dst + (size_t)((i >> 2) * 128 + ((i >> 1) & 1) * 8 + (i & 1)) * 1024) = tr_row(v, i);
      TS(38);
      GT(63);
      if (w == 0) TSDUMP(32);
      return;
    }
    if (wg == 1) {
      mbar_wait(BAR(MB_URAW));
      TS(48);
      uint4* dst = P.xs + X_UT + (i8 * 64 + g) * (U_CH / 16) + (w & 1) * (U_ODD / 16) + U_PAD / 16 + oct * 8 + (w >> 1) * 4 + c;
      const int ln = ((lane >> 1) & 3) + 4 * (lane & 1);
      uint32_t r[8][4];
#pragma unroll
      for (int i = 0; i < 8; i++) ldsm4t(r[i], sb + OFF_STG0 + w * 4096 + ((lane >> 3) * 8 + ln) * 128 + ((i ^ ln) << 4));
#pragma unroll
      for (int i = 0; i < 8; i++) dst[i * (U_CH / 2)] = make_uint4(r[i][0], r[i][1], r[i][2], r[i][3]);
      nb_arrive(NB_INIT, 160);
      if (lane == 0) mbar_arrive(BAR(MB_AUX));
      mbar_wait(BAR(MB_EMPTY + 4));
      mbar_spin(BAR(MB_EMPTY + 6));
    }
    TS(wg * 16 + 1);
  }

  float acc[2][48];
  {
    uint32_t fb = BAR(MB_FULL) + 64 * wg;
    uint32_t da = (uint32_t)mkdesc(sb + OFF_X, 16, 0, 0) + (wg ? 1024 : 3072), db = (uint32_t)mkdesc(sb + OFF_W, 4096, 0, 0);
    constexpr uint64_t ha = mkdesc(0, 0, 1024, 1), hb = mkdesc(0, 0, 512, 2);
    mbar_spin(fb);
    TS(wg * 16 + 2);
#pragma unroll 1
    for (int kb = 0; kb < 8; kb++) {
      WG_FENCE();
#pragma unroll
      for (int k = 0; k < 4; k++) {
        wgmma_ss_n96(acc[0], ha | (da + 2 * k), hb | (db + 64 * k), k ? 1 : kb);
        wgmma_ss_n96(acc[1], ha | (da + 2 * k + 512), hb | (db + 64 * k), k ? 1 : kb);
      }
      WG_COMMIT();
      if (kb < 7) mbar_spin(fb + 8);
      WG_WAIT(1);
      if (kb > 0) e_arrive(fb + 8 * (MB_EMPTY - MB_FULL - 1));
      fb += 8; db += 768;
      da = da == (uint32_t)mkdesc(sb + OFF_X + 65536, 16, 0, 0) ? da - 4096 : da + 1024;
    }
    if (wg == 0) nb_sync(NB_KREAD, 160);
    WG_WAIT(0);
    e_arrive(fb + 8 * (MB_EMPTY - MB_FULL - 1));
    mbar_spin(fb + 8 * (MB_EMPTY - MB_FULL - 1));
  }
  TS(wg * 16 + 3);
  asm volatile("setmaxnreg.inc.sync.aligned.u32 160;");

  constexpr uint32_t stg0 = sb + OFF_STG0, stg1 = sb + OFF_X + 32768;
  uint4* const g_part = P.xs + X_PART;
  uint4* const g_o = P.xs + X_O;
  constexpr uint32_t kvs = stg0;
  auto pack8 = [](const float* a) { return make_uint4(pack_bf(a[0], a[1]), pack_bf(a[2], a[3]), pack_bf(a[4], a[5]), pack_bf(a[6], a[7])); };
  auto feat = [&](const uint4 (&af)[4], float (&p)[4][8]) {
    WG_FENCE();
#pragma unroll
    for (int u = 0; u < 4; u++) wgmma_rs_n16(p[u], af[u], qdesc(sb + OFF_PHI + (u & 1) * 512), 0);
    WG_COMMIT();
  };
  auto packp = [](const float (&p)[4][8], uint32_t (&pw)[16]) {
#pragma unroll
    for (int i = 0; i < 16; i++) pw[i] = pack_bf(p[i >> 2][(i & 1) + 2 * (i & 2)], p[i >> 2][(i & 1) + 2 * (i & 2) + 2]);
  };
  auto contract = [&](float (&kc)[20], uint32_t stg, int acc_in) {
    WG_FENCE();
#pragma unroll
    for (int s = 0; s < 8; s++) wgmma_ss_n40(kc, qdesc(stg + s * SLAB), qdesc(stg + s * SLAB + 2048), s ? 1 : acc_in);
    WG_COMMIT();
    WG_WAIT(0);
  };
  uint32_t eq[32];
  {
    uint4 af[4], aq[4], vp[4];
    float p[4][8];
#pragma unroll
    for (int u = 0; u < 4; u++) af[u] = pack8(acc[u >> 1] + 16 + 8 * (u & 1));
    feat(af, p);
#pragma unroll
    for (int u = 0; u < 4; u++) { aq[u] = pack8(acc[u >> 1] + 8 * (u & 1)); vp[u] = pack8(acc[u >> 1] + 32 + 8 * (u & 1)); }
    WG_WAIT(0);
    uint32_t pw[16], ek[32];
    packp(p, pw);
#pragma unroll
    for (int u = 0; u < 4; u++) dual_exp(pw + 4 * u, ek + 8 * u);
    TS(wg * 16 + 12);
    mbar_wait(BAR(MB_AUX));
    float rs[8][4];
    WG_FENCE();
#pragma unroll
    for (int i = 0; i < 8; i++) wgmma_rs_n8(rs[i], make_uint4(ek[4 * i], ek[4 * i + 1], ek[4 * i + 2], ek[4 * i + 3]), qdesc(sb + OFF_ONE), 0);
    WG_COMMIT();
    feat(aq, p);
    const uint32_t sl = (wg ? stg1 : stg0) + w * SLAB + lane * 16;
#pragma unroll
    for (int i = 0; i < 4; i++) stsm4(sl + (i >> 1) * 4 * SLAB + 2048 + (i & 1) * 512, vp[i].x, vp[i].y, vp[i].z, vp[i].w);
    sts128(sl + (lane >> 4) * (4 * SLAB - 256) + 3072, 0x3F803F80u, 0x3F803F80u, 0x3F803F80u, 0x3F803F80u);
    WG_WAIT(1);
#pragma unroll
    for (int i = 0; i < 8; i++) {
      normalise(ek + 4 * i, rs[i]);
      stsm4(sl + (i >> 2) * 4 * SLAB + (i & 3) * 512, ek[4 * i], ek[4 * i + 1], ek[4 * i + 2], ek[4 * i + 3]);
    }
    asm volatile("fence.proxy.async.shared::cta;" ::: "memory");
    TS(wg * 16 + 13);
    if (wg) {
      nb_arrive(NB_ST0, 256);
    } else {
      float kc[20];
      uint4* pp = g_part + (size_t)(hp * 8 + rt) * 144 + t;
      uint32_t* pz = (uint32_t*)(pp - t + 128) + w * 16 + c * 8 + g;
      asm volatile("" : "+l"(pp), "+l"(pz));
      nb_sync(NB_WG0, 128);
      contract(kc, stg0, 0);
      mbar_wait(BAR(MB_UFULL));
      TS(15);
      nb_sync(NB_ST0, 256);
      contract(kc, stg1, 1);
      TS(6);
      float kv[8];
#pragma unroll
      for (int i = 0; i < 8; i++) kv[i] = w & 2 ? kc[8 + i] : kc[i];
      st_x(pp, nz(pack_bf(kv[0], kv[1])), pack_bf(kv[2], kv[3]), pack_bf(kv[4], kv[5]), pack_bf(kv[6], kv[7]));
      if (c < 2) st_x32(pz, nz(fu(c ? kc[18] : kc[16])));
      TS(5);
    }
    SPLIT();
    WG_WAIT(0);
    packp(p, pw);
#pragma unroll
    for (int u = 0; u < 4; u++) dual_exp(pw + 4 * u, eq + 8 * u);
    SPLIT();
  }
  TS(wg * 16 + 4);
  if (wg == 1) {
    mbar_wait(BAR(MB_UFULL));
    const uint4* ps = g_part + (size_t)hp * 8 * 144 + t;
    const uint32_t* zs = (const uint32_t*)(g_part + (size_t)(hp * 8 + (lane >> 4) * 4) * 144 + 128) + w * 16 + (lane & 15);
    uint4 v[8];
    uint32_t zv[4];
#pragma unroll 1
    for (int it = 0; it < SPIN_MAX; it++) {
#pragma unroll
      for (int i = 0; i < 8; i++) v[i] = ld_x(ps + i * 144);
#pragma unroll
      for (int i = 0; i < 4; i++) zv[i] = ld_x32(zs + i * 576);
      uint32_t m = min(min(zv[0], zv[1]), min(zv[2], zv[3]));
#pragma unroll
      for (int i = 0; i < 8; i++) m = min(m, v[i].x);
      if (__all_sync(0xffffffffu, m != 0)) break;
    }
    float s[8];
    WG_FENCE();
#pragma unroll
    for (int r = 0; r < 8; r++) wgmma_rs_n16(s, v[r], qdesc(sb + OFF_EYE), r);
    WG_COMMIT();
    float zsum = (uf(zv[0]) + uf(zv[1])) + (uf(zv[2]) + uf(zv[3]));
    zsum += __shfl_xor_sync(0xffffffffu, zsum, 16);
    const uint32_t z1 = pack_bf(zsum, 1.f);
    if (lane < 16) sts128(kvs + w * 768 + 512 + lane * 16, z1, z1, z1, z1);
    WG_WAIT(0);
    stsm4(kvs + w * 768 + lane * 16, pack_bf(s[0], s[1]), pack_bf(s[2], s[3]), pack_bf(s[4], s[5]), pack_bf(s[6], s[7]));
    asm volatile("fence.proxy.async.shared::cta;" ::: "memory");
    TS(22);
  }
  nb_sync(NB_KV, 256);
  {
    float n[8][12];
    WG_FENCE();
#pragma unroll
    for (int i = 0; i < 8; i++) wgmma_rs_n24(n[i], make_uint4(eq[4 * i], eq[4 * i + 1], eq[4 * i + 2], eq[4 * i + 3]), qdesc(kvs + (i & 3) * 768), 0);
    WG_COMMIT();
    uint32_t* od = (uint32_t*)(g_o + (size_t)((rt * 4 + wg * 2) * 32 + hp * 2) * 128) + w * 64 + lane;
    WG_WAIT(0);
#pragma unroll
    for (int u = 0; u < 4; u++) {
      float(&np)[12] = n[2 * u];
      const float(&nm)[12] = n[2 * u + 1];
      const float q0 = np[9] * rcp(nm[9]), q1 = np[11] * rcp(nm[11]);
      const float r0 = rcp(fmaf(nm[8], q0, fmaf(np[9], 1e-6f, np[8]))), r1 = rcp(fmaf(nm[10], q1, fmaf(np[11], 1e-6f, np[10])));
#pragma unroll
      for (int i = 0; i < 8; i++) np[i] = fmaf(nm[i], (i & 2) ? q1 : q0, np[i]);
      uint32_t* o = od + (u >> 1) * 16384 + (u & 1) * 512;
      o[0] = pack_bf(np[0] * r0, np[1] * r0);
      o[32] = pack_bf(np[2] * r1, np[3] * r1);
      o[256] = pack_bf(np[4] * r0, np[5] * r0);
      o[288] = pack_bf(np[6] * r1, np[7] * r1);
      if (u == 1) SPLIT();
    }
  }
  TS(wg * 16 + 7);
  nb_arrive(NB_ODONE, 288);
  if (w == 3) {
    nb_sync(NB_OREL + wg, 128);
    if (lane == 0) asm volatile("red.release.gpu.global.add.u32 [%0], 1;" ::"l"((uint32_t*)(P.xs + X_CNT) + (8 + rt) * 32) : "memory");
    if (lane == 0) TS1(57);
    __syncwarp();
  } else {
    nb_arrive(NB_OREL + wg, 128);
  }
  if (wg) { if (w == 0) TSDUMP(16); return; }
  mbar_wait(BAR(MB_WO));
  mbar_wait(BAR(MB_OA));
  TS(8);
  nb_sync(NB_BDONE, 288);
  TS(9);
  float oc[64];
  {
    constexpr uint64_t ha = mkdesc(0, 0, 128, 0), hb = mkdesc(0, 0, 1024, 1);
    constexpr uint32_t da0 = (uint32_t)mkdesc(stg1, 1024, 0, 0), db0 = (uint32_t)mkdesc(sb + OFF_W, 8192, 0, 0);
#pragma unroll 1
    for (int j = 0; j < 8; j++) {
      const int kb = (j + 7) & 7;
      if ((j & 3) == 1) mbar_spin(j == 1 ? BAR(MB_OC) : BAR(MB_OB));
      WG_FENCE();
#pragma unroll
      for (int k = 0; k < 4; k++) wgmma_ss_n128(oc, ha | (da0 + 512 * kb + 128 * k), hb | (db0 + 1024 * kb + 128 * k), k ? 1 : j);
      WG_COMMIT();
    }
    WG_WAIT(0);
  }
  TS(10);
  const uint32_t ot = ((sb + OFF_T + 1023) & ~1023u) + w * 4096;
#pragma unroll
  for (int hf = 0; hf < 2; hf++) {
#pragma unroll
    for (int i = 8 * hf; i < 8 * hf + 8; i += 2)
      stsm4(ot + hf * 2048 + (lane & 15) * 128 + (((i + (lane >> 4)) ^ lane) & 7) * 16, pack_bf(oc[4 * i], oc[4 * i + 1]),
            pack_bf(oc[4 * i + 2], oc[4 * i + 3]), pack_bf(oc[4 * i + 4], oc[4 * i + 5]), pack_bf(oc[4 * i + 6], oc[4 * i + 7]));
    asm volatile("fence.proxy.async.shared::cta;" ::: "memory");
    __syncwarp();
    e_store2d(&mout, ot + hf * 2048, (hp & 3) * 128 + hf * 64, (rt * 4 + (hp >> 2)) * 64 + w * 16);
  }
  asm volatile(ELECT "cp.async.bulk.commit_group;\n@p cp.async.bulk.wait_group.read 0;\n}\n" ::: "memory");
  TS(wg * 16 + 11);
  GT(61 + wg);
  if (w == 0) TSDUMP(0);
  if (w == 1) TSDUMP(48);
}

typedef CUresult (*EncodeFn)(CUtensorMap*, CUtensorMapDataType, cuuint32_t, void*, const cuuint64_t*, const cuuint64_t*,
                             const cuuint32_t*, const cuuint32_t*, CUtensorMapInterleave, CUtensorMapSwizzle,
                             CUtensorMapL2promotion, CUtensorMapFloatOOBfill);

}

extern "C" void kernel_launch(void* const* d_in, const int* in_sizes, int n_in, void* d_out, int out_size) {
  (void)in_sizes; (void)n_in; (void)out_size;
  void* fn = nullptr;
  cudaDriverEntryPointQueryResult qr;
  cudaGetDriverEntryPoint("cuTensorMapEncodeTiled", &fn, cudaEnableDefault, &qr);
  EncodeFn enc = (EncodeFn)fn;
  CUtensorMap mx, mw, mo, mu, mout, mw4;
  const cuuint32_t es[5] = {1, 1, 1, 1, 1};
  {
    cuuint64_t dims[2] = {512, 2048}, st[1] = {1024};
    cuuint32_t box[2] = {64, 128};
    enc(&mx, CU_TENSOR_MAP_DATA_TYPE_BFLOAT16, 2, d_in[0], dims, st, box, es, CU_TENSOR_MAP_INTERLEAVE_NONE,
        CU_TENSOR_MAP_SWIZZLE_128B, CU_TENSOR_MAP_L2_PROMOTION_L2_128B, CU_TENSOR_MAP_FLOAT_OOB_FILL_NONE);
  }
  {
    cuuint64_t dims[3] = {512, 512, 3}, st[2] = {3072, 1024};
    cuuint32_t box[3] = {32, 64, 3};
    enc(&mw, CU_TENSOR_MAP_DATA_TYPE_BFLOAT16, 3, d_in[1], dims, st, box, es, CU_TENSOR_MAP_INTERLEAVE_NONE,
        CU_TENSOR_MAP_SWIZZLE_64B, CU_TENSOR_MAP_L2_PROMOTION_L2_128B, CU_TENSOR_MAP_FLOAT_OOB_FILL_NONE);
  }
  {
    cuuint64_t dims[3] = {64, 512, 8}, st[2] = {1024, 128};
    cuuint32_t box[3] = {64, 64, 2};
    enc(&mo, CU_TENSOR_MAP_DATA_TYPE_BFLOAT16, 3, d_in[3], dims, st, box, es, CU_TENSOR_MAP_INTERLEAVE_NONE,
        CU_TENSOR_MAP_SWIZZLE_128B, CU_TENSOR_MAP_L2_PROMOTION_L2_128B, CU_TENSOR_MAP_FLOAT_OOB_FILL_NONE);
  }
  {
    cuuint64_t dims[4] = {512, 4, 16, 32}, st[3] = {16384, 1024, 65536};
    cuuint32_t box[4] = {64, 4, 16, 2};
    enc(&mu, CU_TENSOR_MAP_DATA_TYPE_BFLOAT16, 4, d_in[4], dims, st, box, es, CU_TENSOR_MAP_INTERLEAVE_NONE,
        CU_TENSOR_MAP_SWIZZLE_128B, CU_TENSOR_MAP_L2_PROMOTION_L2_128B, CU_TENSOR_MAP_FLOAT_OOB_FILL_NONE);
  }
  {
    cuuint64_t dims[2] = {1024, 2048}, st[1] = {2048};
    cuuint32_t box[2] = {64, 16};
    enc(&mout, CU_TENSOR_MAP_DATA_TYPE_BFLOAT16, 2, d_out, dims, st, box, es, CU_TENSOR_MAP_INTERLEAVE_NONE,
        CU_TENSOR_MAP_SWIZZLE_128B, CU_TENSOR_MAP_L2_PROMOTION_NONE, CU_TENSOR_MAP_FLOAT_OOB_FILL_NONE);
  }
  {
    cuuint64_t dims[4] = {512, 64, 3, 8}, st[3] = {3072, 1024, 64 * 3072};
    cuuint32_t box[4] = {32, 64, 3, 4};
    enc(&mw4, CU_TENSOR_MAP_DATA_TYPE_BFLOAT16, 4, d_in[1], dims, st, box, es, CU_TENSOR_MAP_INTERLEAVE_NONE,
        CU_TENSOR_MAP_SWIZZLE_64B, CU_TENSOR_MAP_L2_PROMOTION_L2_128B, CU_TENSOR_MAP_FLOAT_OOB_FILL_NONE);
  }
  Params P;
  P.x = (const __nv_bfloat16*)d_in[0];
  P.wphi = (const __nv_bfloat16*)d_in[2];
  P.wo = (const __nv_bfloat16*)d_in[3];
  P.logA = (const __nv_bfloat16*)d_in[5];
  P.Aim = (const __nv_bfloat16*)d_in[6];
  P.Cre = (const __nv_bfloat16*)d_in[7];
  P.Cim = (const __nv_bfloat16*)d_in[8];
  P.logdt = (const __nv_bfloat16*)d_in[9];
  P.Dskip = (const __nv_bfloat16*)d_in[10];
  P.out = (__nv_bfloat16*)d_out;
  cudaGetSymbolAddress((void**)&P.xs, g_x);
  P.ts = nullptr;
  cudaFuncSetAttribute(fused_kernel, cudaFuncAttributeMaxDynamicSharedMemorySize, SMEM_BYTES);
  fused_kernel<<<NCTA, NTHREADS, SMEM_BYTES>>>(P, mx, mw, mo, mu, mout, mw4);
}
```

```cpp
#include <cuda_runtime.h>
#include <cuda_bf16.h>
#include <cuda_fp16.h>
#include <cuda.h>
#include <stdint.h>

#define DBG_TS 0

namespace {

constexpr int NTHREADS = 512;
constexpr int NCTA = 128;
constexpr int OFF_W = 0;
constexpr int OFF_X = 98304;
constexpr int OFF_U = OFF_X + 65536;
constexpr int U_CH = 4416, U_ODD = 2240, U_PAD = 128;
constexpr int OFF_STG0 = OFF_U + 18432;
constexpr int SLAB = 3328;
constexpr int OFF_T = OFF_STG0 + 8 * SLAB;
constexpr int T_CH = 5216;
constexpr int T_D = 0;
constexpr int T_5 = 2144;
constexpr int T_3 = T_5 + 384;
constexpr int T_7 = T_5 + 1024;
constexpr int T_9 = T_7 + 320;
constexpr int T_KC = T_9 + 320;
constexpr int T_ST = T_5 - 1024;
constexpr int OFF_PHI = OFF_T + 4 * T_CH;
constexpr int OFF_EYE = OFF_PHI + 1024, OFF_ONE = OFF_EYE + 512;
constexpr int OFF_BAR = OFF_ONE + 256;
constexpr int SMEM_BYTES = OFF_BAR + 512 + 256 * DBG_TS;
constexpr uint32_t SB = 1024;
static_assert(T_KC + 2 * 656 <= T_CH, "table size");
static_assert(SMEM_BYTES <= 232448, "smem");
constexpr int MB_URAW = 0, MB_FULL = 1  , MB_WO = 17, MB_UFULL = 18, MB_OA = 19, MB_OB = 20, MB_OC = 21,
              MB_EMPTY = 22  , MB_AUX = 38;
__host__ __device__ constexpr uint32_t BAR(int i) { return SB + OFF_BAR + 8 * i; }
constexpr int NB_WG0 = 1, NB_ODONE = 2, NB_ST0 = 3  , NB_KV = 5, NB_YZ = 6, NB_INIT = 7, NB_PREP = 8, NB_PROD = 9, NB_KREAD = 10, NB_BDONE = 11, NB_OREL = 12  ;
#define U_AT 2
#define ZERO_STEP 12
constexpr int SPIN_MAX = 1 << 16;

constexpr int X_CNT = 0;
constexpr int X_PART = 256;
constexpr int X_O = X_PART + 16 * 8 * 144;
constexpr int X_Y = X_O + 32 * 32 * 128;
constexpr int X_UT = X_Y + 512 * 8 * 32;
constexpr int X_SIZE = X_UT + 512 * (U_CH / 16);
__device__ __align__(128) uint4 g_x[X_SIZE];
extern __shared__ uint8_t smem_raw[];
#define TS(i) do {} while (0)
#define TS1(i) do {} while (0)
#define GT(i) do {} while (0)
#define TSDUMP(base) do {} while (0)

__device__ __forceinline__ uint32_t smem_u32(const void* p) { return (uint32_t)__cvta_generic_to_shared(p); }
__device__ __forceinline__ void mbar_arrive(uint32_t b) {
  asm volatile("mbarrier.arrive.shared::cta.b64 _, [%0];" ::"r"(b) : "memory");
}
__device__ __forceinline__ void mbar_wait(uint32_t b) {
  uint32_t done = 0;
#pragma unroll 1
  for (int i = 0; i < SPIN_MAX && !done; i++) {
    asm volatile("{\n.reg .pred p;\nmbarrier.try_wait.parity.shared::cta.b64 p, [%1], 0, 4000;\nselp.u32 %0, 1, 0, p;\n}\n"
                 : "=r"(done) : "r"(b) : "memory");
  }
}
__device__ __forceinline__ void mbar_spin(uint32_t b) {
  uint32_t done = 0;
#pragma unroll 1
  for (int i = 0; i < (SPIN_MAX << 4) && !done; i++) {
    asm volatile("{\n.reg .pred p;\nmbarrier.try_wait.parity.shared::cta.b64 p, [%1], 0;\nselp.u32 %0, 1, 0, p;\n}\n"
                 : "=r"(done) : "r"(b) : "memory");
  }
}
__device__ __forceinline__ void mbar_init(uint32_t b, int n) {
  asm volatile("mbarrier.init.shared::cta.b64 [%0], %1;" ::"r"(b), "r"(n) : "memory");
}
__device__ __forceinline__ void mbar_expect(uint32_t b, int bytes) {
  asm volatile("mbarrier.arrive.expect_tx.shared::cta.b64 _, [%0], %1;" ::"r"(b), "r"(bytes) : "memory");
}
__device__ __forceinline__ void nb_sync(int id, int n) { asm volatile("bar.sync %0, %1;" ::"r"(id), "r"(n) : "memory"); }
__device__ __forceinline__ void nb_arrive(int id, int n) { asm volatile("bar.arrive %0, %1;" ::"r"(id), "r"(n) : "memory"); }
#define ELECT "{\n.reg .pred p;\nelect.sync _|p, 0xffffffff;\n@p "
__device__ __forceinline__ void e_arrive(uint32_t b) {
  asm volatile(ELECT "mbarrier.arrive.shared::cta.b64 _, [%0];\n}\n" ::"r"(b) : "memory");
}
__device__ __forceinline__ void e_expect(uint32_t b, int bytes) {
  asm volatile(ELECT "mbarrier.arrive.expect_tx.shared::cta.b64 _, [%0], %1;\n}\n" ::"r"(b), "r"(bytes) : "memory");
}
__device__ __forceinline__ void e_tma2d(uint32_t dst, const CUtensorMap* m, uint32_t bar, int c0, int c1) {
  asm volatile(ELECT "cp.async.bulk.tensor.2d.shared::cluster.global.mbarrier::complete_tx::bytes [%0], [%1, {%3,%4}], [%2];\n}\n"
               ::"r"(dst), "l"(m), "r"(bar), "r"(c0), "r"(c1) : "memory");
}
__device__ __forceinline__ void e_tma3d(uint32_t dst, const CUtensorMap* m, uint32_t bar, int c0, int c1, int c2) {
  asm volatile(ELECT "cp.async.bulk.tensor.3d.shared::cluster.global.mbarrier::complete_tx::bytes [%0], [%1, {%3,%4,%5}], [%2];\n}\n"
               ::"r"(dst), "l"(m), "r"(bar), "r"(c0), "r"(c1), "r"(c2) : "memory");
}
__device__ __forceinline__ void e_tma4d(uint32_t dst, const CUtensorMap* m, uint32_t bar, int c0, int c3) {
  asm volatile(ELECT "cp.async.bulk.tensor.4d.shared::cluster.global.mbarrier::complete_tx::bytes [%0], [%1, {%3,%5,%5,%4}], [%2];\n}\n"
               ::"r"(dst), "l"(m), "r"(bar), "r"(c0), "r"(c3), "r"(0) : "memory");
}
__device__ __forceinline__ void e_bulk(uint32_t dst, const void* src, int bytes, uint32_t bar) {
  asm volatile(ELECT "cp.async.bulk.shared::cluster.global.mbarrier::complete_tx::bytes [%0], [%1], %2, [%3];\n}\n"
               ::"r"(dst), "l"(src), "r"(bytes), "r"(bar) : "memory");
}
__device__ __forceinline__ void e_prefetch(const void* p, int bytes) {
  asm volatile(ELECT "cp.async.bulk.prefetch.L2.global [%0], %1;\n}\n" ::"l"(p), "r"(bytes) : "memory");
}
__device__ __forceinline__ void e_store2d(const CUtensorMap* m, uint32_t src, int c0, int c1) {
  asm volatile(ELECT "cp.async.bulk.tensor.2d.global.shared::cta.bulk_group [%0, {%2,%3}], [%1];\n}\n"
               ::"l"(m), "r"(src), "r"(c0), "r"(c1) : "memory");
}
__host__ __device__ constexpr uint64_t mkdesc(uint32_t addr, uint32_t lbo, uint32_t sbo, int swz) {
  return (uint64_t)((addr & 0x3FFFF) >> 4) | ((uint64_t)(lbo >> 4) << 16) | ((uint64_t)(sbo >> 4) << 32) |
         ((uint64_t)swz << 62);
}
#define SPLIT() asm volatile("{\n.reg .pred p;\nsetp.eq.u32 p, %0, %1;\n@p exit;\n}\n" ::"r"(blockIdx.y), "n"(__LINE__) : "memory")
#define WG_FENCE() asm volatile("wgmma.fence.sync.aligned;" ::: "memory")
#define WG_COMMIT() asm volatile("wgmma.commit_group.sync.aligned;" ::: "memory")
#define WG_WAIT(n) asm volatile("wgmma.wait_group.sync.aligned " #n ";" ::: "memory")

__device__ __forceinline__ void mma(float& d0, float& d1, float& d2, float& d3, uint32_t a0, uint32_t a1, uint32_t a2,
                                    uint32_t a3, uint32_t b0, uint32_t b1) {
  asm volatile("mma.sync.aligned.m16n8k16.row.col.f32.bf16.bf16.f32 {%0,%1,%2,%3},{%4,%5,%6,%7},{%8,%9},{%0,%1,%2,%3};"
               : "+f"(d0), "+f"(d1), "+f"(d2), "+f"(d3)
               : "r"(a0), "r"(a1), "r"(a2), "r"(a3), "r"(b0), "r"(b1));
}
__device__ __forceinline__ void mmac(float (&d)[4], uint32_t a0, uint32_t a1, uint32_t a2, uint32_t a3, uint32_t b0,
                                     uint32_t b1, const float (&c)[4]) {
  asm volatile("mma.sync.aligned.m16n8k16.row.col.f32.bf16.bf16.f32 {%0,%1,%2,%3},{%4,%5,%6,%7},{%8,%9},{%10,%11,%12,%13};"
               : "=f"(d[0]), "=f"(d[1]), "=f"(d[2]), "=f"(d[3])
               : "r"(a0), "r"(a1), "r"(a2), "r"(a3), "r"(b0), "r"(b1), "f"(c[0]), "f"(c[1]), "f"(c[2]), "f"(c[3]));
}
__device__ __forceinline__ void mma_p(int p, float (&d)[4], uint32_t a0, uint32_t a1, uint32_t a2, uint32_t a3, uint32_t b0, uint32_t b1) {
  asm volatile("{\n.reg .pred q;\nsetp.ne.b32 q, %10, 0;\n"
               "@q mma.sync.aligned.m16n8k16.row.col.f32.bf16.bf16.f32 {%0,%1,%2,%3},{%4,%5,%6,%7},{%8,%9},{%0,%1,%2,%3};\n}\n"
               : "+f"(d[0]), "+f"(d[1]), "+f"(d[2]), "+f"(d[3])
               : "r"(a0), "r"(a1), "r"(a2), "r"(a3), "r"(b0), "r"(b1), "r"(p));
}
__device__ __forceinline__ void mmac_p(int p, float (&d)[4], uint32_t a0, uint32_t a1, uint32_t a2, uint32_t a3, uint32_t b0,
                                       uint32_t b1, const float (&c)[4]) {
  asm volatile("{\n.reg .pred q;\nsetp.ne.b32 q, %14, 0;\n"
               "@q mma.sync.aligned.m16n8k16.row.col.f32.bf16.bf16.f32 {%0,%1,%2,%3},{%4,%5,%6,%7},{%8,%9},{%10,%11,%12,%13};\n}\n"
               : "+f"(d[0]), "+f"(d[1]), "+f"(d[2]), "+f"(d[3])
               : "r"(a0), "r"(a1), "r"(a2), "r"(a3), "r"(b0), "r"(b1), "f"(c[0]), "f"(c[1]), "f"(c[2]), "f"(c[3]), "r"(p));
}
__device__ __forceinline__ void mma_h(float (&d)[4], const uint32_t (&a)[4], uint32_t b0, uint32_t b1) {
  asm volatile("mma.sync.aligned.m16n8k16.row.col.f32.f16.f16.f32 {%0,%1,%2,%3},{%4,%5,%6,%7},{%8,%9},{%0,%1,%2,%3};"
               : "+f"(d[0]), "+f"(d[1]), "+f"(d[2]), "+f"(d[3]) : "r"(a[0]), "r"(a[1]), "r"(a[2]), "r"(a[3]), "r"(b0), "r"(b1));
}
__device__ __forceinline__ void mma0(float& d0, float& d1, float& d2, float& d3, uint32_t a0, uint32_t a1, uint32_t a2,
                                     uint32_t a3, uint32_t b0, uint32_t b1) {
  asm volatile("mma.sync.aligned.m16n8k16.row.col.f32.bf16.bf16.f32 {%0,%1,%2,%3},{%4,%5,%6,%7},{%8,%9},{%10,%10,%10,%10};"
               : "=f"(d0), "=f"(d1), "=f"(d2), "=f"(d3)
               : "r"(a0), "r"(a1), "r"(a2), "r"(a3), "r"(b0), "r"(b1), "f"(0.f));
}
__device__ __forceinline__ uint32_t pack_bf(float lo, float hi) {
  uint32_t r;
  asm("cvt.rn.bf16x2.f32 %0, %1, %2;" : "=r"(r) : "f"(hi), "f"(lo));
  return r;
}
__device__ __forceinline__ float bf_lo(uint32_t w) { return __uint_as_float(w << 16); }
__device__ __forceinline__ float bf_hi(uint32_t w) { return __uint_as_float(w & 0xffff0000u); }
__device__ __forceinline__ float bf_round(float x) { return __bfloat162float(__float2bfloat16_rn(x)); }
__device__ __forceinline__ uint32_t bmax2(uint32_t a, uint32_t b) {
  uint32_t r; asm("max.bf16x2 %0, %1, %2;" : "=r"(r) : "r"(a), "r"(b)); return r;
}
__device__ __forceinline__ uint32_t bmin2(uint32_t a, uint32_t b) {
  uint32_t r; asm("min.bf16x2 %0, %1, %2;" : "=r"(r) : "r"(a), "r"(b)); return r;
}
__device__ __forceinline__ float ex2(float x) { float r; asm("ex2.approx.ftz.f32 %0, %1;" : "=f"(r) : "f"(x)); return r; }
__device__ __forceinline__ float rcp(float x) { float r; asm("rcp.approx.ftz.f32 %0, %1;" : "=f"(r) : "f"(x)); return r; }
__device__ __forceinline__ void ldsm4(uint32_t (&r)[4], uint32_t a) {
  asm volatile("ldmatrix.sync.aligned.m8n8.x4.shared.b16 {%0,%1,%2,%3}, [%4];"
               : "=r"(r[0]), "=r"(r[1]), "=r"(r[2]), "=r"(r[3]) : "r"(a) : "memory");
}
__device__ __forceinline__ void ldsm4t(uint32_t (&r)[4], uint32_t a) {
  asm volatile("ldmatrix.sync.aligned.m8n8.x4.trans.shared.b16 {%0,%1,%2,%3}, [%4];"
               : "=r"(r[0]), "=r"(r[1]), "=r"(r[2]), "=r"(r[3]) : "r"(a) : "memory");
}
__device__ __forceinline__ void stsm4(uint32_t a, uint32_t r0, uint32_t r1, uint32_t r2, uint32_t r3) {
  asm volatile("stmatrix.sync.aligned.m8n8.x4.shared.b16 [%0], {%1,%2,%3,%4};"
               ::"r"(a), "r"(r0), "r"(r1), "r"(r2), "r"(r3) : "memory");
}
__device__ __forceinline__ uint32_t lds32(uint32_t a) {
  uint32_t r; asm volatile("ld.shared.u32 %0, [%1];" : "=r"(r) : "r"(a) : "memory"); return r;
}
__device__ __forceinline__ uint32_t lds16(uint32_t a) {
  uint32_t r; asm volatile("{\n.reg .u16 h;\nld.shared.u16 h, [%1];\ncvt.u32.u16 %0, h;\n}\n" : "=r"(r) : "r"(a) : "memory"); return r;
}
__device__ __forceinline__ uint2 lds64(uint32_t a) {
  uint2 r; asm volatile("ld.shared.v2.u32 {%0,%1}, [%2];" : "=r"(r.x), "=r"(r.y) : "r"(a) : "memory"); return r;
}
__device__ __forceinline__ uint4 lds128(uint32_t a) {
  uint4 r;
  asm volatile("ld.shared.v4.u32 {%0,%1,%2,%3}, [%4];" : "=r"(r.x), "=r"(r.y), "=r"(r.z), "=r"(r.w) : "r"(a) : "memory");
  return r;
}
__device__ __forceinline__ void sts32(uint32_t a, uint32_t v) { asm volatile("st.shared.u32 [%0], %1;" ::"r"(a), "r"(v) : "memory"); }
__device__ __forceinline__ void sts16(uint32_t a, uint32_t v) {
  asm volatile("{\n.reg .u16 h;\ncvt.u16.u32 h, %1;\nst.shared.u16 [%0], h;\n}\n" ::"r"(a), "r"(v) : "memory");
}
__device__ __forceinline__ void sts64(uint32_t a, uint32_t x, uint32_t y) {
  asm volatile("st.shared.v2.u32 [%0], {%1,%2};" ::"r"(a), "r"(x), "r"(y) : "memory");
}
__device__ __forceinline__ void sts128(uint32_t a, uint32_t x, uint32_t y, uint32_t z, uint32_t w) {
  asm volatile("st.shared.v4.u32 [%0], {%1,%2,%3,%4};" ::"r"(a), "r"(x), "r"(y), "r"(z), "r"(w) : "memory");
}
__device__ __forceinline__ uint4 ld_x(const uint4* p) {
  uint4 r;
  asm volatile("{\n.reg .b128 t;\nld.relaxed.gpu.global.b128 t, [%4];\nmov.b128 {%0,%1,%2,%3}, t;\n}\n"
               : "=r"(r.x), "=r"(r.y), "=r"(r.z), "=r"(r.w) : "l"(p) : "memory");
  return r;
}
__device__ __forceinline__ uint32_t ld_x32(const uint32_t* p) {
  uint32_t r; asm volatile("ld.relaxed.gpu.global.u32 %0, [%1];" : "=r"(r) : "l"(p) : "memory"); return r;
}
__device__ __forceinline__ void st_x(uint4* p, uint32_t x, uint32_t y, uint32_t z, uint32_t w) {
  asm volatile("{\n.reg .b128 t;\nmov.b128 t, {%1,%2,%3,%4};\nst.relaxed.gpu.global.b128 [%0], t;\n}\n"
               ::"l"(p), "r"(x), "r"(y), "r"(z), "r"(w) : "memory");
}
__device__ __forceinline__ void st_x_p(int p, uint4* a, uint32_t x, uint32_t y, uint32_t z, uint32_t w) {
  asm volatile("{\n.reg .b128 t;\n.reg .pred q;\nsetp.ne.b32 q, %5, 0;\nmov.b128 t, {%1,%2,%3,%4};\n@q st.relaxed.gpu.global.b128 [%0], t;\n}\n"
               ::"l"(a), "r"(x), "r"(y), "r"(z), "r"(w), "r"(p) : "memory");
}
__device__ __forceinline__ void sts64_p(int p, uint32_t a, uint32_t x, uint32_t y) {
  asm volatile("{\n.reg .pred q;\nsetp.ne.b32 q, %3, 0;\n@q st.shared.v2.u32 [%0], {%1,%2};\n}\n" ::"r"(a), "r"(x), "r"(y), "r"(p) : "memory");
}
__device__ __forceinline__ void st_x32(uint32_t* p, uint32_t x) {
  asm volatile("st.relaxed.gpu.global.u32 [%0], %1;" ::"l"(p), "r"(x) : "memory");
}
__device__ __forceinline__ uint32_t nz(uint32_t w) { return max(w, 1u); }
__device__ __forceinline__ uint32_t fu(float x) { return __float_as_uint(x); }
__device__ __forceinline__ float uf(uint32_t x) { return __uint_as_float(x); }

__device__ __forceinline__ void wgmma_ss_n96(float (&d)[48], uint64_t da, uint64_t db, int sc) {
  asm volatile("{\n.reg .pred p;\nsetp.ne.b32 p, %50, 0;\n"
      "wgmma.mma_async.sync.aligned.m64n96k16.f32.bf16.bf16 "
      "{%0,%1,%2,%3,%4,%5,%6,%7,%8,%9,%10,%11,%12,%13,%14,%15,%16,%17,%18,%19,%20,%21,%22,%23,%24,%25,%26,%27,%28,%29,%30,%31,%32,%33,%34,%35,%36,%37,%38,%39,%40,%41,%42,%43,%44,%45,%46,%47}, "
      "%48, %49, p, 1, 1, 0, 1;\n}\n"
      : "+f"(d[0]), "+f"(d[1]), "+f"(d[2]), "+f"(d[3]), "+f"(d[4]), "+f"(d[5]), "+f"(d[6]), "+f"(d[7]),
        "+f"(d[8]), "+f"(d[9]), "+f"(d[10]), "+f"(d[11]), "+f"(d[12]), "+f"(d[13]), "+f"(d[14]), "+f"(d[15]),
        "+f"(d[16]), "+f"(d[17]), "+f"(d[18]), "+f"(d[19]), "+f"(d[20]), "+f"(d[21]), "+f"(d[22]), "+f"(d[23]),
        "+f"(d[24]), "+f"(d[25]), "+f"(d[26]), "+f"(d[27]), "+f"(d[28]), "+f"(d[29]), "+f"(d[30]), "+f"(d[31]),
        "+f"(d[32]), "+f"(d[33]), "+f"(d[34]), "+f"(d[35]), "+f"(d[36]), "+f"(d[37]), "+f"(d[38]), "+f"(d[39]),
        "+f"(d[40]), "+f"(d[41]), "+f"(d[42]), "+f"(d[43]), "+f"(d[44]), "+f"(d[45]), "+f"(d[46]), "+f"(d[47])
      : "l"(da), "l"(db), "r"(sc));
}

__device__ __forceinline__ void wgmma_ss_n128(float (&d)[64], uint64_t da, uint64_t db, int sc) {
  asm volatile("{\n.reg .pred p;\nsetp.ne.b32 p, %66, 0;\n"
      "wgmma.mma_async.sync.aligned.m64n128k16.f32.bf16.bf16 "
      "{%0,%1,%2,%3,%4,%5,%6,%7,%8,%9,%10,%11,%12,%13,%14,%15,%16,%17,%18,%19,%20,%21,%22,%23,%24,%25,%26,%27,%28,%29,%30,%31,%32,%33,%34,%35,%36,%37,%38,%39,%40,%41,%42,%43,%44,%45,%46,%47,%48,%49,%50,%51,%52,%53,%54,%55,%56,%57,%58,%59,%60,%61,%62,%63}, "
      "%64, %65, p, 1, 1, 0, 1;\n}\n"
      : "+f"(d[0]), "+f"(d[1]), "+f"(d[2]), "+f"(d[3]), "+f"(d[4]), "+f"(d[5]), "+f"(d[6]), "+f"(d[7]),
        "+f"(d[8]), "+f"(d[9]), "+f"(d[10]), "+f"(d[11]), "+f"(d[12]), "+f"(d[13]), "+f"(d[14]), "+f"(d[15]),
        "+f"(d[16]), "+f"(d[17]), "+f"(d[18]), "+f"(d[19]), "+f"(d[20]), "+f"(d[21]), "+f"(d[22]), "+f"(d[23]),
        "+f"(d[24]), "+f"(d[25]), "+f"(d[26]), "+f"(d[27]), "+f"(d[28]), "+f"(d[29]), "+f"(d[30]), "+f"(d[31]),
        "+f"(d[32]), "+f"(d[33]), "+f"(d[34]), "+f"(d[35]), "+f"(d[36]), "+f"(d[37]), "+f"(d[38]), "+f"(d[39]),
        "+f"(d[40]), "+f"(d[41]), "+f"(d[42]), "+f"(d[43]), "+f"(d[44]), "+f"(d[45]), "+f"(d[46]), "+f"(d[47]),
        "+f"(d[48]), "+f"(d[49]), "+f"(d[50]), "+f"(d[51]), "+f"(d[52]), "+f"(d[53]), "+f"(d[54]), "+f"(d[55]),
        "+f"(d[56]), "+f"(d[57]), "+f"(d[58]), "+f"(d[59]), "+f"(d[60]), "+f"(d[61]), "+f"(d[62]), "+f"(d[63])
      : "l"(da), "l"(db), "r"(sc));
}

__device__ __forceinline__ void wgmma_ss_n40(float (&d)[20], uint64_t da, uint64_t db, int sc) {
  asm volatile("{\n.reg .pred p;\nsetp.ne.b32 p, %22, 0;\n"
      "wgmma.mma_async.sync.aligned.m64n40k16.f32.bf16.bf16 "
      "{%0,%1,%2,%3,%4,%5,%6,%7,%8,%9,%10,%11,%12,%13,%14,%15,%16,%17,%18,%19}, "
      "%20, %21, p, 1, 1, 1, 1;\n}\n"
      : "+f"(d[0]), "+f"(d[1]), "+f"(d[2]), "+f"(d[3]), "+f"(d[4]), "+f"(d[5]), "+f"(d[6]), "+f"(d[7]),
        "+f"(d[8]), "+f"(d[9]), "+f"(d[10]), "+f"(d[11]), "+f"(d[12]), "+f"(d[13]), "+f"(d[14]), "+f"(d[15]),
        "+f"(d[16]), "+f"(d[17]), "+f"(d[18]), "+f"(d[19])
      : "l"(da), "l"(db), "r"(sc));
}

__device__ __forceinline__ void wgmma_rs_n8(float (&d)[4], const uint4& a, uint64_t db, int sc) {
  asm volatile("{\n.reg .pred p;\nsetp.ne.b32 p, %9, 0;\n"
      "wgmma.mma_async.sync.aligned.m64n8k16.f32.bf16.bf16 "
      "{%0,%1,%2,%3}, "
      "{%4,%5,%6,%7}, %8, p, 1, 1, 1;\n}\n"
      : "+f"(d[0]), "+f"(d[1]), "+f"(d[2]), "+f"(d[3])
      : "r"(a.x), "r"(a.y), "r"(a.z), "r"(a.w), "l"(db), "r"(sc));
}

__device__ __forceinline__ void wgmma_rs_n16(float (&d)[8], const uint4& a, uint64_t db, int sc) {
  asm volatile("{\n.reg .pred p;\nsetp.ne.b32 p, %13, 0;\n"
      "wgmma.mma_async.sync.aligned.m64n16k16.f32.bf16.bf16 "
      "{%0,%1,%2,%3,%4,%5,%6,%7}, "
      "{%8,%9,%10,%11}, %12, p, 1, 1, 1;\n}\n"
      : "+f"(d[0]), "+f"(d[1]), "+f"(d[2]), "+f"(d[3]), "+f"(d[4]), "+f"(d[5]), "+f"(d[6]), "+f"(d[7])
      : "r"(a.x), "r"(a.y), "r"(a.z), "r"(a.w), "l"(db), "r"(sc));
}

__device__ __forceinline__ void wgmma_rs_n24(float (&d)[12], const uint4& a, uint64_t db, int sc) {
  asm volatile("{\n.reg .pred p;\nsetp.ne.b32 p, %17, 0;\n"
      "wgmma.mma_async.sync.aligned.m64n24k16.f32.bf16.bf16 "
      "{%0,%1,%2,%3,%4,%5,%6,%7,%8,%9,%10,%11}, "
      "{%12,%13,%14,%15}, %16, p, 1, 1, 1;\n}\n"
      : "+f"(d[0]), "+f"(d[1]), "+f"(d[2]), "+f"(d[3]), "+f"(d[4]), "+f"(d[5]), "+f"(d[6]), "+f"(d[7]),
        "+f"(d[8]), "+f"(d[9]), "+f"(d[10]), "+f"(d[11])
      : "r"(a.x), "r"(a.y), "r"(a.z), "r"(a.w), "l"(db), "r"(sc));
}

struct Params {
  const __nv_bfloat16 *logA, *Aim, *Cre, *Cim, *logdt, *Dskip, *x, *wphi, *wo;
  __nv_bfloat16* out;
  uint4* xs;
  long long* ts;
};

__device__ __forceinline__ uint4 tr_row(const uint4 (&v)[8], int i) {
  uint32_t o[4];
#pragma unroll
  for (int m = 0; m < 4; m++) {
    const uint4 &ra = v[2 * m], &rb = v[2 * m + 1];
    const int k = i >> 1;
    const uint32_t xa = k == 0 ? ra.x : k == 1 ? ra.y : k == 2 ? ra.z : ra.w;
    const uint32_t xb = k == 0 ? rb.x : k == 1 ? rb.y : k == 2 ? rb.z : rb.w;
    o[m] = __byte_perm(xa, xb, (i & 1) ? 0x7632 : 0x5410);
  }
  return make_uint4(o[0], o[1], o[2], o[3]);
}

struct cpx { float r, i; };
__device__ __forceinline__ cpx csq(cpx a) { return {a.r * a.r - a.i * a.i, 2.f * (a.r * a.i)}; }
__device__ __forceinline__ cpx polar(float e, float t) {
  const float m = ex2(e);
  return {m * __cosf(t), m * __sinf(t)};
}

struct KgenRaw { unsigned short la, ai, cr, ci, ldt; };
__device__ __forceinline__ KgenRaw kgen_load(const Params& P, int d, int unit, int lane) {
  const int o = d * 128 + unit * 32 + lane;
  return {__ldg((const unsigned short*)P.logA + o), __ldg((const unsigned short*)P.Aim + o), __ldg((const unsigned short*)P.Cre + o),
          __ldg((const unsigned short*)P.Cim + o), __ldg((const unsigned short*)P.logdt + d)};
}
struct hmul { __half2 a, b; };
__device__ __forceinline__ hmul mk_mul(cpx w) {
  uint32_t b;
  asm("{\n.reg .f32 n;\nneg.ftz.f32 n, %1;\ncvt.rn.f16x2.f32 %0, %2, n;\n}\n" : "=r"(b) : "f"(w.i), "f"(w.r));
  return {__floats2half2_rn(w.r, w.i), *(const __half2*)&b};
}
__device__ __forceinline__ __half2 hcm(__half2 z, const hmul& w) { return __hfma2(__high2half2(z), w.b, __hmul2(__low2half2(z), w.a)); }
__device__ __forceinline__ uint32_t hu(__half2 v) { return *(const uint32_t*)&v; }

struct KgenAddr { uint32_t sa, sb, lb, lc, la; };
__device__ __forceinline__ KgenAddr kgen_addr(int lane, uint32_t buf) {
  KgenAddr a;
  a.sa = buf + (lane & 7) * 128 + ((((lane >> 3) ^ lane) & 7) << 4);
  a.lb = buf + (lane >> 3) * 128 + (((lane ^ (lane >> 3)) & 7) << 4);
  a.la = buf + ((lane >> 3) & 1) * 1024 + (lane >> 4) * 128 + (((lane ^ (lane >> 4)) & 7) << 4);
  a.sb = a.sa ^ 64; a.lc = a.lb ^ 64;
  asm volatile("" : "+r"(a.sa), "+r"(a.sb), "+r"(a.lb), "+r"(a.lc), "+r"(a.la));
  return a;
}
__device__ __forceinline__ void kgen_unit(const KgenRaw& r, const KgenAddr& ad, uint32_t zero, float (&k)[5][4], float& k2048, float& sc) {
  const float dt = bf_round(expf(bf_lo(r.ldt)));
  const float a2 = bf_round(ex2(bf_lo(r.la) * 1.4426950408889634f)) * (dt * -1.4426950408889634f);
  const float f = bf_lo(r.ai) * dt;
  const float r128 = f * 20.371832715762604f;
  const uint32_t ex = min(max(__reduce_max_sync(0xffffffffu, max(r.cr & 0x7fffu, r.ci & 0x7fffu)) >> 7, 1u), 253u);
  const float cs = uf((254u - ex) << 23);
  sc = 2.f * dt * uf(ex << 23);
  const cpx C = {bf_lo(r.cr) * cs, -bf_lo(r.ci) * cs};
  auto put = [&](const __half2 (&v)[8], uint32_t off) {
    stsm4(ad.sa + off, hu(v[0]), hu(v[1]), hu(v[2]), hu(v[3]));
    stsm4(ad.sb + off, hu(v[4]), hu(v[5]), hu(v[6]), hu(v[7]));
  };
  uint32_t A[4][4], B[5][2][4];
  auto get = [&](int j, uint32_t off) {
    __syncwarp();
    ldsm4(B[j][0], ad.lb + off);
    ldsm4(B[j][1], ad.lc + 512 + off);
  };
  auto tile = [&](int j) {
    k[j][0] = k[j][1] = k[j][2] = k[j][3] = 0.f;
#pragma unroll
    for (int s = 0; s < 4; s++) mma_h(k[j], A[s], B[j][s >> 1][2 * (s & 1)], B[j][s >> 1][2 * (s & 1) + 1]);
  };
  auto after = [&](cpx v, uint32_t dep) { return cpx{uf(fu(v.r) ^ (dep & zero)), v.i}; };
  const cpx w1 = polar(a2, f), w128 = polar(a2 * 128.f, (r128 - rintf(r128)) * 6.283185307179586f);
  const cpx w2 = csq(w1), w4 = csq(w2);
  __half2 t0[8], t1[8], t2[8], t3[8], t4[8];
  const hmul m2 = mk_mul(w2), m4 = mk_mul(w4), m128 = mk_mul(w128);
  t0[0] = __floats2half2_rn(1.f, 0.f); t0[1] = __floats2half2_rn(w1.r, w1.i); t0[2] = m2.a; t0[4] = m4.a;
  t0[3] = hcm(t0[1], m2); t0[5] = hcm(t0[1], m4); t0[6] = hcm(t0[2], m4); t0[7] = hcm(t0[3], m4);
  put(t0, 0); get(0, 0);
  t1[0] = m128.a;
#pragma unroll
  for (int i = 1; i < 8; i++) t1[i] = hcm(t0[i], m128);
  put(t1, 1024); get(1, 1024);
  {
    cpx w8 = csq(after(w4, B[0][0][0]));
    w8.i = -w8.i;
    const cpx w16 = csq(w8), w32 = csq(w16), w64 = csq(w32);
    const hmul m8 = mk_mul(w8), m16 = mk_mul(w16), m32 = mk_mul(w32), m64 = mk_mul(w64);
    __half2 a[8];
    a[0] = __floats2half2_rn(C.r, C.i); a[1] = hcm(a[0], m8);
    a[2] = hcm(a[0], m16); a[3] = hcm(a[1], m16);
#pragma unroll
    for (int i = 0; i < 4; i++) a[4 + i] = hcm(a[i], m32);
    put(a, 0);
#pragma unroll
    for (int i = 0; i < 8; i++) a[i] = hcm(a[i], m64);
    put(a, 1024);
    __syncwarp();
#pragma unroll
    for (int s = 0; s < 4; s++) ldsm4(A[s], (ad.la ^ (s << 5)) + s * 256);
  }
  const cpx w256 = csq(after(w128, B[1][0][0]));
  const hmul m256 = mk_mul(w256);
  t2[0] = m256.a;
#pragma unroll
  for (int i = 1; i < 8; i++) t2[i] = hcm((i & 1) ? t1[i & 6] : t0[i & 6], m256);
  put(t2, 0); get(2, 0);
  tile(0); tile(1);
  const cpx w512 = csq(after(w256, A[0][0]));
  const hmul m512 = mk_mul(w512);
  t3[0] = m512.a;
#pragma unroll
  for (int i = 1; i < 8; i++) t3[i] = hcm((i & 2) ? t2[i & 5] : ((i & 1) ? t1[i & 4] : t0[i & 4]), m512);
  put(t3, 1024); get(3, 1024);
  tile(2);
  const cpx w1024 = csq(after(w512, B[2][0][0])), we = csq(w1024);
  const hmul m1024 = mk_mul(w1024);
  t4[0] = m1024.a;
#pragma unroll
  for (int i = 1; i < 8; i++) t4[i] = hcm((i & 4) ? t3[i & 3] : ((i & 2) ? t2[i & 1] : t1[0]), m1024);
  put(t4, 0); get(4, 0);
  tile(3); tile(4);
  k2048 = (C.r * we.r + C.i * we.i) * sc;
}

__device__ __forceinline__ void build_tables(uint32_t tb, int lane, float (&k)[5][4], float k2048) {
  const int g = lane >> 2, c = lane & 3;
  const uint32_t kc = tb + T_KC + 16;
  {
    const uint32_t a0 = kc + 16 * g + 4 * c, a2 = kc + 2 * (256 + 4 * g + c);
    const uint32_t a3 = kc + 2 * (384 + 2 * g + 64 * (c & 1) + (c >> 1)), a4 = kc + 2 * (512 + g + 32 * c);
#pragma unroll
    for (int r = 0; r < 2; r++) {
      sts32(a0 + 128 * r, pack_bf(k[0][2 * r], k[0][2 * r + 1]));
      sts32(a0 + 128 * r + 256, pack_bf(k[1][2 * r], k[1][2 * r + 1]));
      const uint32_t w2 = pack_bf(k[2][2 * r], k[2][2 * r + 1]);
      const uint32_t w3 = pack_bf(k[3][2 * r], k[3][2 * r + 1]);
      const uint32_t w4 = pack_bf(k[4][2 * r], k[4][2 * r + 1]);
      sts16(a2 + 64 * r, w2); sts16(a2 + 64 * r + 128, w2 >> 16);
      sts16(a3 + 32 * r, w3); sts16(a3 + 32 * r + 64, w3 >> 16);
      sts16(a4 + 16 * r, w4); sts16(a4 + 16 * r + 32, w4 >> 16);
    }
  }
  if (lane == 0) { sts16(kc + 2 * 640, pack_bf(k2048, 0.f)); sts32(kc - 4, 0); }
  __syncwarp();
  const uint32_t td = tb + T_D + 32;
#pragma unroll
  for (int hf = 0; hf < 2; hf++) {
    const uint2 v = lds64(kc + 256 * hf + 8 * lane);
    const uint32_t pv = lds32(kc + 256 * hf + 8 * lane - 4);
    sts128(td + 512 * hf + 16 * lane, __byte_perm(v.x, pv, 0x7610), __byte_perm(v.x, v.x, 0x1032), __byte_perm(v.y, v.x, 0x7610),
           __byte_perm(v.y, v.y, 0x1032));
  }
#pragma unroll
  for (int hf = 0; hf < 2; hf++) {
    const uint32_t v = lds32(kc + 512 + 128 * hf + 4 * lane), nx = lds32(kc + 516 + 128 * hf + 4 * lane);
    uint32_t w0 = __byte_perm(v, v, 0x1010);
    const uint32_t w1 = w0;
    if (hf == 0) { const uint32_t pv = lds32(kc + 508); if (lane == 0) w0 = __byte_perm(v, pv, 0x7610); }
    sts128(td + 1024 + 512 * hf + 16 * lane, w0, w1, __byte_perm(v, v, 0x1032), __byte_perm(nx, v, 0x7610));
  }
  {
    const uint32_t kk = lds16(kc + 2 * 384);
    const uint32_t w = lane < 3 ? (kk | (kk << 16)) : (lane == 3 ? (kk << 16) : 0u);
    if (lane < 24) sts32(td + 4 * (lane < 16 ? 512 + lane : lane - 24), w);
    const uint32_t lo_ = lds16(kc + 2 * 511), le_ = lds16(kc + 2 * 512);
    const uint32_t ja = tb + T_5 + (lane < 16 ? 4 * lane : 256 + 4 * lane);
    sts32(ja, lane == 16 ? (le_ << 16) : 0u);
    sts32(ja + 384, lane == 16 ? (lo_ << 16) : 0u);
    sts32(tb + (lane < 16 ? T_7 : T_9 - 64) + 4 * lane, 0u);
  }
#pragma unroll
  for (int s = 0; s < 2; s++) {
    const uint32_t b = kc + 2 * (s ? 512 : 384) + 8 * lane;
    const uint2 v = lds64(b);
    uint32_t em = lds16(b - 2), e0 = v.x;
    const uint32_t e4 = lds16(b + 8);
    if (lane == 0) { em = 0; e0 = 0; }
    sts64(tb + (s ? T_7 : T_3) + 64 + 8 * lane, __byte_perm(v.x, em, 0x5432), __byte_perm(v.y, v.x, 0x7632));
    sts64(tb + (s ? T_9 : T_5) + 64 + 8 * lane, __byte_perm(v.y, e0, 0x5410), __byte_perm(e4, v.y, 0x5410));
  }
  __syncwarp();
}

__device__ __forceinline__ uint32_t box2w(int lo, int n, int o) {
  return ((unsigned)(o - lo) < (unsigned)n ? 0x3F80u : 0u) | ((unsigned)(o + 1 - lo) < (unsigned)n ? 0x3F800000u : 0u);
}

__device__ __forceinline__ void conv_channel(uint32_t ub, uint32_t tb, int lane, uint4* ydst) {
  const int g = lane >> 2, c = lane & 3, x = g - 2 * c;
  const int mi = lane >> 3;
  const uint32_t qa = ub + U_PAD + 16 * (lane & 7) + ((mi == 0 || mi == 3) ? U_ODD : 0) - (mi == 0 ? 16 : 0);
  const uint32_t hb = ub + U_PAD + (mi & 1) * U_ODD + 16 * ((lane >> 4) + (lane & 7)) - 16;
  const uint32_t kv = lds16(tb + T_KC + 16 + 2 * 512);
  const int oh = c < 2 ? 8 + 2 * c : 2 * c - 8, og = c < 3 ? 2 * c : -10;
  uint32_t bx[4] = {box2w(g - 4, 9, 2 * c), box2w(g - 3, 7, 2 * c), box2w(g - 4, 9, oh), box2w(g - 3, 7, oh)};
  uint32_t by[4] = {box2w(g - 10, 5, 2 * c - 8), box2w(g - 5, 3, 2 * c - 8), box2w(g - 10, 5, og), box2w(g - 5, 3, og)};
  uint32_t lb0 = ((unsigned)(x + 5) < 2u ? kv : 0u) | ((unsigned)(x + 4) < 2u ? kv << 16 : 0u);
  uint32_t lb1 = ((unsigned)(x - 3) < 2u ? kv : 0u) | ((unsigned)(x - 4) < 2u ? kv << 16 : 0u);
  const int q0 = g - 1, q1 = c < 3 ? g : g - 2;
  uint32_t y0a = ub + U_PAD + (q0 & 1) * U_ODD + 16 * (q0 >> 1) + 4 * c;
  uint32_t y1a = ub + U_PAD + (q1 & 1) * U_ODD + 16 * (q1 >> 1) + 4 * c;
#pragma unroll
  for (int i = 0; i < 4; i++) asm volatile("" : "+r"(bx[i]), "+r"(by[i]));
  asm volatile("" : "+r"(lb0), "+r"(lb1), "+r"(y0a), "+r"(y1a));
  mbar_wait(BAR(MB_UFULL));
  mbar_wait(BAR(MB_EMPTY + 15));
  TS(36);
  float acc[16][4];
  {
    uint32_t z09[8], z07[8], zm9[8], zm7[8];
#pragma unroll
    for (int i = 0; i < 8; i++) {
      uint32_t h[4];
      ldsm4(h, hb + 128 * i);
      float y0, y1, y2, y3, w0, w1, w2, w3;
      mma0(y0, y1, y2, y3, bx[0], bx[1], bx[2], bx[3], h[2], c < 2 ? h[3] : h[1]);
      mma0(w0, w1, w2, w3, bx[0], bx[1], bx[2], bx[3], h[1], c < 2 ? h[2] : h[0]);
      z09[i] = pack_bf(y0, y1); z07[i] = pack_bf(y2, y3);
      zm9[i] = pack_bf(w0, w1); zm7[i] = pack_bf(w2, w3);
    }
  uint32_t f3[3][4][4];
  {
    const uint32_t fa = tb + T_7 + 4 * (16 + x);
#pragma unroll
    for (int tt = 0; tt < 3; tt++)
#pragma unroll
      for (int D = 0; D < 4; D++) {
        const uint32_t a = fa + (tt == 0 ? 316 : (tt == 1 ? 320 : 0)) + 64 * D;
        f3[tt][D][0] = lds32(a); f3[tt][D][1] = lds32(a + 32); f3[tt][D][2] = lds32(a - 32); f3[tt][D][3] = lds32(a);
      }
  }
    float a[4][2][4];
#pragma unroll
    for (int kap = 0; kap < 4; kap++)
#pragma unroll
      for (int sg = 0; sg < 2; sg++)
#pragma unroll
        for (int bk = 3; bk >= kap; bk--) {
          const uint32_t(&q0_)[4] = f3[sg ? 2 : 0][bk - kap];
          const uint32_t(&q1_)[4] = f3[sg ? 2 : 1][bk - kap];
          float(&a0)[4] = a[bk][0];
          float(&a1)[4] = a[bk][1];
          if (sg == 0 && kap == 0) {
            mma0(a0[0], a0[1], a0[2], a0[3], q0_[0], q0_[1], q0_[2], q0_[3], z09[0], z09[1]);
            mma0(a1[0], a1[1], a1[2], a1[3], q1_[0], q1_[1], q1_[2], q1_[3], zm9[0], zm9[1]);
          } else {
            mma(a0[0], a0[1], a0[2], a0[3], q0_[0], q0_[1], q0_[2], q0_[3], sg ? zm7[2 * kap] : z09[2 * kap], sg ? zm7[2 * kap + 1] : z09[2 * kap + 1]);
            mma(a1[0], a1[1], a1[2], a1[3], q1_[0], q1_[1], q1_[2], q1_[3], sg ? z07[2 * kap] : zm9[2 * kap], sg ? z07[2 * kap + 1] : zm9[2 * kap + 1]);
          }
        }
    SPLIT();
#pragma unroll
    for (int i = 0; i < 8; i++) {
      uint32_t h[4];
      ldsm4(h, qa + 128 * i);
      const float ci[4] = {a[i >> 1][0][2 * (i & 1)], a[i >> 1][0][2 * (i & 1) + 1], a[i >> 1][1][2 * (i & 1)], a[i >> 1][1][2 * (i & 1) + 1]};
      mmac(acc[8 + i], h[0], h[1], h[2], h[3], lb0, lb1, ci);
    }
  }
  TS(44);
  {
    uint2 a5[10], a3[10];
    const uint32_t aa = tb + T_5 + 4 * (8 + 2 * g - 2 * c);
#pragma unroll
    for (int m = 0; m < 10; m++) { a5[m] = lds64(aa + 32 * m); a3[m] = lds64(aa + 384 + 32 * m); }
    uint32_t x5[12][2], x3[12][2];
    auto ygen = [&](int kap) {
#pragma unroll
      for (int hh = 0; hh < 2; hh++) {
        float y0, y1, y2, y3;
        mma0(y0, y1, y2, y3, by[0], by[1], by[2], by[3], lds32(y0a + 128 * kap + 64 * hh), lds32(y1a + 128 * kap + 64 * hh));
        x5[kap][hh] = pack_bf(y0, y1);
        x3[kap][hh] = pack_bf(y2, y3);
      }
    };
    ygen(11); ygen(10); ygen(9); ygen(8);
#pragma unroll
    for (int kap = 11; kap >= 0; kap--) {
      if (kap >= 4) ygen(kap - 4);
#pragma unroll
      for (int sg = 0; sg < 2; sg++)
#pragma unroll
        for (int i = 4; i >= 0; i--) {
          const int be = kap + 4 + i;
          if (be <= 15) {
            const uint2 &hi = sg ? a3[2 * i + 1] : a5[2 * i + 1], &lo = sg ? a3[2 * i] : a5[2 * i];
            const uint32_t b0 = sg ? x3[kap][0] : x5[kap][0], b1 = sg ? x3[kap][1] : x5[kap][1];
            if (be < 8 && i == 0 && sg == 0) mma0(acc[be][0], acc[be][1], acc[be][2], acc[be][3], hi.x, hi.y, lo.x, lo.y, b0, b1);
            else mma(acc[be][0], acc[be][1], acc[be][2], acc[be][3], hi.x, hi.y, lo.x, lo.y, b0, b1);
          }
        }
    }
  }
  TS(45);
  {
    const uint32_t st = tb + T_ST + lane * 8;
#pragma unroll
    for (int be = 4; be < 12; be++) sts64(st + 256 * be, pack_bf(acc[be][0], acc[be][1]), pack_bf(acc[be][2], acc[be][3]));
    SPLIT();
    uint32_t F[66], qd[8][4];
    const uint32_t fa = tb + T_D + 32 + 4 * x;
#pragma unroll
    for (int i = 0; i < 32; i++) {
      const int s = 120 - (i >> 2) - 8 * (i & 3);
      uint32_t(&q)[4] = qd[i & 7];
      ldsm4(q, qa + 16 * s);
      const int m = 16 * (i & 3) + 2 * (i >> 2);
      F[m] = lds32(fa + 32 * m); F[m + 1] = lds32(fa + 32 * m + 32);
#pragma unroll
      for (int be = 15; be >= 12; be--) {
        const int de = 8 * be - s;
        float(&a)[4] = (be >= 14 && !(i & 1)) ? acc[be - 4] : acc[be];
        if (de >= 0 && be >= 14 && i == 2 * (15 - be)) mma0(a[0], a[1], a[2], a[3], q[0], q[1], q[2], q[3], F[2 * de + 1], F[2 * de]);
        else if (de >= 0) mma(a[0], a[1], a[2], a[3], q[0], q[1], q[2], q[3], F[2 * de + 1], F[2 * de]);
      }
    }
#pragma unroll
    for (int i = 0; i < 8; i++) acc[14 + (i >> 2)][i & 3] += acc[10 + (i >> 2)][i & 3];
    F[64] = lds32(fa + 32 * 64); F[65] = lds32(fa + 32 * 65);
    uint32_t qp = qa + 128 * 11, sta = st + 256 * 10;
    uint4* yd = ydst + 7 * 32;
#pragma unroll
    for (int i = 0; i < 6; i++) ldsm4(qd[i], qp - 16 * i);
    uint2 sv = lds64(sta + 256);
    float ci[4] = {bf_lo(sv.x), bf_hi(sv.x), bf_lo(sv.y), bf_hi(sv.y)};
    float T[5][4];
#pragma unroll
    for (int i = 0; i < 16; i++) T[i >> 2][i & 3] = acc[12 + (i >> 2)][i & 3];
    nb_sync(NB_YZ, 160);
    TS(46);
#pragma unroll 1
    for (int bp = 5; bp >= 0; bp--) {
      uint32_t held[2];
#pragma unroll
      for (int o = 1; o >= 0; o--) {
#pragma unroll
        for (int k = 4; k >= 1; k--) mmac(T[k], qd[0][0], qd[0][1], qd[0][2], qd[0][3], F[16 * k + 1], F[16 * k], T[k - 1]);
        mmac(T[0], qd[0][0], qd[0][1], qd[0][2], qd[0][3], F[1], F[0], ci);
        ldsm4(qd[6], qp - 16 * 6);
        ldsm4(qd[7], qp - 16 * 7);
        sv = lds64(sta);
#pragma unroll
        for (int i = 1; i < 8; i++) {
#pragma unroll
          for (int k = 3; k >= 0; k--)
            mma(T[k][0], T[k][1], T[k][2], T[k][3], qd[i][0], qd[i][1], qd[i][2], qd[i][3], F[16 * k + 2 * i + 1], F[16 * k + 2 * i]);
          if (i < 7) ldsm4(qd[i - 1], qp - 128 - 16 * (i - 1));
          if (i == 2) {
            const uint32_t w0 = pack_bf(T[4][0], T[4][1]), w1 = pack_bf(T[4][2], T[4][3]);
            if (o) { held[0] = w0; held[1] = w1; }
            else st_x(yd, nz(w0), w1, held[0], held[1]);
          }
          if (i == 4) {
            if (2 * bp + o <= 4) sv = make_uint2(0, 0);
            ci[0] = bf_lo(sv.x); ci[1] = bf_hi(sv.x); ci[2] = bf_lo(sv.y); ci[3] = bf_hi(sv.y);
          }
        }
        qp -= 128; sta -= 256;
      }
      yd -= 32;
    }
#pragma unroll
    for (int B = 1; B >= 0; B--)
      st_x(ydst + B * 32, nz(pack_bf(T[2 * B][0], T[2 * B][1])), pack_bf(T[2 * B][2], T[2 * B][3]),
           pack_bf(T[2 * B + 1][0], T[2 * B + 1][1]), pack_bf(T[2 * B + 1][2], T[2 * B + 1][3]));
  }
}

__device__ __forceinline__ void dual_exp(const uint32_t* w, uint32_t* e) {
  const float L = 1.44268798828125f;
  uint32_t mx = bmax2(bmax2(w[0], w[1]), bmax2(w[2], w[3]));
  uint32_t mn = bmin2(bmin2(w[0], w[1]), bmin2(w[2], w[3]));
  mx = bmax2(mx, __shfl_xor_sync(0xffffffffu, mx, 1));
  mn = bmin2(mn, __shfl_xor_sync(0xffffffffu, mn, 1));
  mx = bmax2(mx, __shfl_xor_sync(0xffffffffu, mx, 2));
  mn = bmin2(mn, __shfl_xor_sync(0xffffffffu, mn, 2));
  const float mx0 = bf_lo(mx) * -L, mx1 = bf_hi(mx) * -L, mn0 = bf_lo(mn) * L, mn1 = bf_hi(mn) * L;
#pragma unroll
  for (int i = 0; i < 2; i++) {
    const float a0 = bf_lo(w[2 * i]), a1 = bf_hi(w[2 * i]), b0 = bf_lo(w[2 * i + 1]), b1 = bf_hi(w[2 * i + 1]);
    e[2 * i] = pack_bf(ex2(fmaf(a0, L, mx0)), ex2(fmaf(b0, L, mx0)));
    e[2 * i + 1] = pack_bf(ex2(fmaf(a1, L, mx1)), ex2(fmaf(b1, L, mx1)));
    e[4 + 2 * i] = pack_bf(ex2(fmaf(a0, -L, mn0)), ex2(fmaf(b0, -L, mn0)));
    e[5 + 2 * i] = pack_bf(ex2(fmaf(a1, -L, mn1)), ex2(fmaf(b1, -L, mn1)));
  }
}
__device__ __forceinline__ void normalise(uint32_t* e, const float (&s)[4]) {
  const uint32_t r = pack_bf(rcp(s[0]), rcp(s[2]));
  const __nv_bfloat162 rr = *(const __nv_bfloat162*)&r;
#pragma unroll
  for (int i = 0; i < 4; i++) {
    const __nv_bfloat162 v = __hmul2(*(const __nv_bfloat162*)&e[i], (i & 1) ? __high2bfloat162(rr) : __low2bfloat162(rr));
    e[i] = *(const uint32_t*)&v;
  }
}
__host__ __device__ constexpr uint64_t qdesc(uint32_t addr) { return mkdesc(addr, 128, 256, 0); }

__global__ void __launch_bounds__(NTHREADS, 1)
fused_kernel(const Params P, const __grid_constant__ CUtensorMap mx, const __grid_constant__ CUtensorMap mw,
             const __grid_constant__ CUtensorMap mo, const __grid_constant__ CUtensorMap mu,
             const __grid_constant__ CUtensorMap mout, const __grid_constant__ CUtensorMap mw4) {
  constexpr uint32_t sb = SB;
  const int tid = threadIdx.x, lane = tid & 31;
  const int warp = __shfl_sync(0xffffffffu, tid >> 5, 0);
  const int b = blockIdx.x, oct = b >> 3, i8 = b & 7;
  const int rt = oct < 8 ? oct : 15 - oct;
  const int hp = (oct >> 3) * 8 + i8;

  const int wg = warp >> 2, w = warp & 3;
  const int d = b * 4 + ((tid >> 5) & 3);
  if (tid < 384) {
    asm volatile("prefetch.tensormap [%0];" ::"l"(&mu) : "memory");
    asm volatile("prefetch.tensormap [%0];" ::"l"(&mw) : "memory");
    asm volatile("prefetch.tensormap [%0];" ::"l"(&mx) : "memory");
    asm volatile("prefetch.tensormap [%0];" ::"l"(&mw4) : "memory");
  }
  if (warp == 12) {
    if (lane == 0) {
#pragma unroll
      for (int i = 0; i < 9; i++) mbar_init(BAR(i), 1);
      asm volatile("fence.mbarrier_init.release.cluster;" ::: "memory");
    }
    __syncwarp();
    if (lane < 9) mbar_expect(BAR(0) + 8 * lane, lane == 5 ? 65536 : ((lane == 0 || lane > 5) ? 16384 : 28672));
    __syncwarp();
    e_tma3d(sb + OFF_W, &mw, BAR(MB_FULL), hp * 32, 0, 0);
    e_tma2d(sb + OFF_X + 3 * 16384, &mx, BAR(MB_FULL), 0, rt * 256);
    nb_arrive(NB_PROD, 192);
  } else if (warp == 13) {
    if (lane == 0) {
#pragma unroll
      for (int i = 9; i < 39; i++) mbar_init(BAR(i), i < MB_EMPTY ? 1 : (i < MB_AUX ? 4 : 8));
      asm volatile("fence.mbarrier_init.release.cluster;" ::: "memory");
    }
    __syncwarp();
    if (lane < 9) mbar_expect(BAR(MB_FULL + 8) + 8 * lane, lane < 8 ? 16384 : 131072);
    nb_arrive(NB_PROD, 192);
  }
  const KgenRaw raw = kgen_load(P, d, tid >> 7, lane);
  const unsigned short dsk = __ldg((const unsigned short*)P.Dskip + d);
  const uint32_t tb = sb + OFF_T + w * T_CH;
  const uint32_t kp = wg >= 2 ? sb + OFF_STG0 + 16384 + w * 2048 : ((tb + 127) & ~127u) + wg * 2048;
  const KgenAddr kad = kgen_addr(lane, wg == 3 ? sb + OFF_X + 32768 + w * 2048 : kp);
  if (wg == 1) nb_sync(NB_PROD, 192);
  if (warp == 12) {
#pragma unroll 1
    for (int kb = 1; kb < 4; kb++) {
      if (kb == U_AT) e_tma4d(sb + OFF_STG0, &mu, BAR(MB_URAW), i8 * 64, oct * 2);
      e_tma3d(sb + OFF_W + kb * 12288, &mw, BAR(MB_FULL) + 8 * kb, hp * 32, kb * 64, 0);
      e_tma2d(sb + OFF_X + (kb < 2 ? kb + 3 : kb - 2) * 16384, &mx, BAR(MB_FULL) + 8 * kb, kb * 64, rt * 256);
    }
    e_prefetch(P.x + (size_t)(rt * 256 + hp * 16) * 512, 16384);
    e_tma4d(sb + OFF_W + 4 * 12288, &mw4, BAR(MB_FULL + 4), hp * 32, 4);
    if (smem_u32(smem_raw) != SB) __trap();
    if (lane == 0) TS1(54);
  }
  float k[5][4], k2048, ksc;
  kgen_unit(raw, kad, blockIdx.y, k, k2048, ksc);
  TS(40 + wg);
  if ((fu(k[0][0]) & fu(k[1][0]) & fu(k[2][0]) & fu(k[3][0]) & fu(k[4][0])) == 0xffffffffu) sts32(kp, 0);
  if (wg == 3) {
    nb_sync(0, 512);
    if (warp == 12) {
      asm volatile("fence.proxy.async.shared::cta;" ::: "memory");
      e_tma2d(sb + OFF_X + 2 * 16384, &mx, BAR(MB_FULL + 4), 256, rt * 256);
    }
  } else if (wg) {
    nb_arrive(0, 512);
  }
  k2048 += __shfl_xor_sync(0xffffffffu, k2048, 16);
  k2048 += __shfl_xor_sync(0xffffffffu, k2048, 8);
  if (wg != 2) {
    uint32_t h[10];
#pragma unroll
    for (int j = 0; j < 10; j++) h[j] = hu(__floats2half2_rn(k[j >> 1][2 * (j & 1)], k[j >> 1][2 * (j & 1) + 1]));
    sts128(kp + lane * 16, h[0], h[1], h[2], h[3]);
    sts128(kp + 512 + lane * 16, h[4], h[5], h[6], h[7]);
    sts128(kp + 1024 + lane * 16, h[8], h[9], fu(k2048), fu(ksc));
  }
  if (wg == 0) { nb_arrive(NB_PREP, 512); nb_sync(0, 512); }
  else if (wg != 2) nb_arrive(NB_PREP, 512);
  else nb_sync(NB_PREP, 512);
  if (warp >= 12) {
    asm volatile("setmaxnreg.dec.sync.aligned.u32 32;");
    if (warp == 12) {
      uint32_t slot = sb + OFF_X + 3 * 16384;
#pragma unroll 1
      for (int n = 0; n < 11; n++) {
        mbar_spin(BAR(MB_EMPTY) + 8 * n);
        const int m = n + 5;
        e_tma2d(slot, &mx, BAR(MB_FULL) + 8 * m, (m & 7) * 64, rt * 256 + (m >> 3) * 128);
        slot = slot == sb + OFF_X + 4 * 16384 ? sb + OFF_X : slot + 16384;
        if (n == 7) {
          e_prefetch(P.wo + (size_t)b * 2048, 4096);
          asm volatile("prefetch.tensormap [%0];" ::"l"(&mo) : "memory");
          asm volatile("prefetch.tensormap [%0];" ::"l"(&mout) : "memory");
        }
      }
#pragma unroll 1
      for (int i = 0; i < 8; i++) {
        mbar_wait(BAR(MB_EMPTY + 10) + 8 * ((0x54332100u >> (4 * i)) & 7));
        const int w0 = (0x54736210u >> (4 * i)) & 7;
        e_tma3d(sb + OFF_W + w0 * 16384, &mo, BAR(MB_WO), 0, w0 * 64, (hp & 3) * 2);
      }
    } else {
      if (warp == 15) {
        const uint4 v0 = __ldg((const uint4*)P.wphi + hp * 64 + lane), v1 = __ldg((const uint4*)P.wphi + hp * 64 + 32 + lane);
        sts128(sb + OFF_PHI + (lane & 1) * 256 + (lane >> 1) * 16, v0.x, v0.y, v0.z, v0.w);
        sts128(sb + OFF_PHI + 512 + (lane & 1) * 256 + (lane >> 1) * 16, v1.x, v1.y, v1.z, v1.w);
        const uint32_t one = (((lane >> 3) ^ (lane >> 4)) & 1) ? 0u : ((lane & 1) ? 0x3F800000u : 0x3F80u);
        const int q = (lane >> 1) & 3;
        sts128(sb + OFF_EYE + lane * 16, q == 0 ? one : 0u, q == 1 ? one : 0u, q == 2 ? one : 0u, q == 3 ? one : 0u);
        sts64(sb + OFF_ONE + lane * 8, 0x3F803F80u, 0x3F803F80u);
        asm volatile("fence.proxy.async.shared::cta;" ::: "memory");
        nb_arrive(NB_KREAD, 160);
      }
      uint32_t* cnt = (uint32_t*)(P.xs + X_CNT) + (warp == 13 ? i8 : (warp == 14 ? 8 + rt : 16 + oct)) * 32;
      const unsigned target = (ld_x32(cnt) & ~31u) + 32;
      if (warp != 14) {
        if (warp == 15) mbar_wait(BAR(MB_EMPTY + ZERO_STEP));
        uint4* pz = P.xs + (warp == 13 ? X_PART + (hp * 8 + rt) * 144 : X_Y + b * 1024) + lane;
#pragma unroll 1
        for (int i = (warp == 13 ? 144 : 1024) - lane; i > 0; i -= 32, pz += 32) st_x(pz, 0, 0, 0, 0);
        if (warp == 15) __syncwarp();
        else nb_sync(NB_INIT, 160);
        if (lane == 0) TS1(warp == 13 ? 49 : 52);
        if (lane == 0) asm volatile("red.release.gpu.global.add.u32 [%0], %1;" ::"l"(cnt), "r"(warp == 15 ? 4 : 2) : "memory");
        if (lane == 0) TS1(warp == 13 ? 50 : 53);
        if (warp == 13 && (lane & 1)) cnt += ((b >> 4) - i8) * 32;
      } else {
        nb_sync(NB_ODONE, 288);
        asm volatile("fence.proxy.async.shared::cta;" ::: "memory");
      }
      {
        const unsigned t0 = clock();
        unsigned v0 = ld_x32(cnt);
        while (clock() - t0 < 220u) {}
        unsigned v1 = ld_x32(cnt);
        while (clock() - t0 < 440u) {}
        unsigned v2 = ld_x32(cnt);
#pragma unroll 1
        for (int i = 0; i < SPIN_MAX; i++) {
          if (__all_sync(0xffffffffu, (int)(v0 - target) >= 0)) break;
          v0 = ld_x32(cnt);
          if (__all_sync(0xffffffffu, (int)(v1 - target) >= 0)) break;
          v1 = ld_x32(cnt);
          if (__all_sync(0xffffffffu, (int)(v2 - target) >= 0)) break;
          v2 = ld_x32(cnt);
        }
        asm volatile("fence.acq_rel.cta;" ::: "memory");
      }
      if (lane == 0) TS1(warp == 13 ? 51 : (warp == 14 ? 58 : 55));
      if (warp == 15) { nb_arrive(NB_YZ, 160); return; }
      asm volatile("fence.proxy.async.global;" ::: "memory");
      if (warp == 13) {
        mbar_wait(BAR(MB_EMPTY + 11));
        e_expect(BAR(MB_UFULL), 4 * U_CH);
        e_bulk(sb + OFF_U, P.xs + X_UT + b * (U_CH / 4), 4 * U_CH, BAR(MB_UFULL));
      } else {
        const uint4* src = P.xs + X_O + (rt * 4 + (hp >> 2)) * 4096;
        e_expect(BAR(MB_OA), 14336);
        e_bulk(sb + OFF_STG0, src + 3200, 14336, BAR(MB_OA));
        e_expect(BAR(MB_OC), 32768);
        e_bulk(sb + OFF_X + 32768, src, 32768, BAR(MB_OC));
        nb_sync(NB_BDONE, 288);
        asm volatile("fence.proxy.async.shared::cta;" ::: "memory");
        e_expect(BAR(MB_OB), 18432);
        e_bulk(sb + OFF_U, src + 2048, 18432, BAR(MB_OB));
      }
    }
    return;
  }

  const int t = tid & 127;
  const int g = lane >> 2, c = lane & 3;
  {
    if (wg == 2) {
      asm volatile("setmaxnreg.inc.sync.aligned.u32 160;");
#pragma unroll
      for (int j = 0; j < 5; j++) { k[j][0] *= ksc; k[j][1] *= ksc; k[j][2] *= ksc; k[j][3] *= ksc; }
#pragma unroll 1
      for (int q = 0; q < 3; q++) {
        const uint32_t src = (q == 2 ? kp : ((tb + 127) & ~127u) + q * 2048) + lane * 16;
        const uint4 v0 = lds128(src), v1 = lds128(src + 512), v2 = lds128(src + 1024);
        const uint32_t h[10] = {v0.x, v0.y, v0.z, v0.w, v1.x, v1.y, v1.z, v1.w, v2.x, v2.y};
#pragma unroll
        for (int j = 0; j < 10; j++) {
          const float2 f = __half22float2(*(const __half2*)&h[j]);
          k[j >> 1][2 * (j & 1)] = fmaf(f.x, uf(v2.w), k[j >> 1][2 * (j & 1)]);
          k[j >> 1][2 * (j & 1) + 1] = fmaf(f.y, uf(v2.w), k[j >> 1][2 * (j & 1) + 1]);
        }
        k2048 += uf(v2.z);
      }
#pragma unroll
      for (int o2 = 4; o2; o2 >>= 1) k2048 += __shfl_xor_sync(0xffffffffu, k2048, o2);
      if (lane == 0) k[0][0] += bf_lo(dsk);
      __syncwarp();
      if (lane == 0) mbar_arrive(BAR(MB_AUX));
      TS(34);
      build_tables(tb, lane, k, k2048);
      TS(35);
      uint4* const g_y = P.xs + X_Y;
      conv_channel(sb + OFF_U + w * U_CH, tb, lane, g_y + (size_t)d * 256 + lane);
      nb_arrive(NB_BDONE, 288);
      TS(37);
      const int lam = w * 8 + g;
      const uint4* src = g_y + (size_t)(oct * 32 + c * 8) * 256 + i8 * 32 + lam;
      uint4 v[8];
#pragma unroll 1
      for (int it = 0; it < SPIN_MAX; it++) {
        uint32_t m = 0xffffffffu;
#pragma unroll
        for (int i = 0; i < 8; i++) v[i] = ld_x(src + i * 256);
#pragma unroll
        for (int i = 0; i < 8; i++) m = min(m, v[i].x);
        if (__all_sync(0xffffffffu, m != 0)) break;
      }
      __nv_bfloat16* dst = P.out + (size_t)(i8 * 256 + (lam >> 2) * 16 + (lam & 3) * 2) * 1024 + 512 + oct * 32 + c * 8;
#pragma unroll
      for (int i = 0; i < 8; i++) *(uint4*)(dst + (size_t)((i >> 2) * 128 + ((i >> 1) & 1) * 8 + (i & 1)) * 1024) = tr_row(v, i);
      TS(38);
      GT(63);
      if (w == 0) TSDUMP(32);
      return;
    }
    if (wg == 1) {
      mbar_wait(BAR(MB_URAW));
      TS(48);
      uint4* dst = P.xs + X_UT + (i8 * 64 + g) * (U_CH / 16) + (w & 1) * (U_ODD / 16) + U_PAD / 16 + oct * 8 + (w >> 1) * 4 + c;
      const int ln = ((lane >> 1) & 3) + 4 * (lane & 1);
      uint32_t r[8][4];
#pragma unroll
      for (int i = 0; i < 8; i++) ldsm4t(r[i], sb + OFF_STG0 + w * 4096 + ((lane >> 3) * 8 + ln) * 128 + ((i ^ ln) << 4));
#pragma unroll
      for (int i = 0; i < 8; i++) dst[i * (U_CH / 2)] = make_uint4(r[i][0], r[i][1], r[i][2], r[i][3]);
      nb_arrive(NB_INIT, 160);
      if (lane == 0) mbar_arrive(BAR(MB_AUX));
      mbar_wait(BAR(MB_EMPTY + 4));
      mbar_spin(BAR(MB_EMPTY + 6));
    }
    TS(wg * 16 + 1);
  }

  float acc[2][48];
  {
    uint32_t fb = BAR(MB_FULL) + 64 * wg;
    uint32_t da = (uint32_t)mkdesc(sb + OFF_X, 16, 0, 0) + (wg ? 1024 : 3072), db = (uint32_t)mkdesc(sb + OFF_W, 4096, 0, 0);
    constexpr uint64_t ha = mkdesc(0, 0, 1024, 1), hb = mkdesc(0, 0, 512, 2);
    mbar_spin(fb);
    TS(wg * 16 + 2);
#pragma unroll 1
    for (int kb = 0; kb < 8; kb++) {
      WG_FENCE();
#pragma unroll
      for (int k = 0; k < 4; k++) {
        wgmma_ss_n96(acc[0], ha | (da + 2 * k), hb | (db + 64 * k), k ? 1 : kb);
        wgmma_ss_n96(acc[1], ha | (da + 2 * k + 512), hb | (db + 64 * k), k ? 1 : kb);
      }
      WG_COMMIT();
      if (kb < 7) mbar_spin(fb + 8);
      WG_WAIT(1);
      if (kb > 0) e_arrive(fb + 8 * (MB_EMPTY - MB_FULL - 1));
      fb += 8; db += 768;
      da = da == (uint32_t)mkdesc(sb + OFF_X + 65536, 16, 0, 0) ? da - 4096 : da + 1024;
    }
    if (wg == 0) nb_sync(NB_KREAD, 160);
    WG_WAIT(0);
    e_arrive(fb + 8 * (MB_EMPTY - MB_FULL - 1));
    mbar_spin(fb + 8 * (MB_EMPTY - MB_FULL - 1));
  }
  TS(wg * 16 + 3);
  asm volatile("setmaxnreg.inc.sync.aligned.u32 160;");

  constexpr uint32_t stg0 = sb + OFF_STG0, stg1 = sb + OFF_X + 32768;
  uint4* const g_part = P.xs + X_PART;
  uint4* const g_o = P.xs + X_O;
  constexpr uint32_t kvs = stg0;
  auto pack8 = [](const float* a) { return make_uint4(pack_bf(a[0], a[1]), pack_bf(a[2], a[3]), pack_bf(a[4], a[5]), pack_bf(a[6], a[7])); };
  auto feat = [&](const uint4 (&af)[4], float (&p)[4][8]) {
    WG_FENCE();
#pragma unroll
    for (int u = 0; u < 4; u++) wgmma_rs_n16(p[u], af[u], qdesc(sb + OFF_PHI + (u & 1) * 512), 0);
    WG_COMMIT();
  };
  auto packp = [](const float (&p)[4][8], uint32_t (&pw)[16]) {
#pragma unroll
    for (int i = 0; i < 16; i++) pw[i] = pack_bf(p[i >> 2][(i & 1) + 2 * (i & 2)], p[i >> 2][(i & 1) + 2 * (i & 2) + 2]);
  };
  auto contract = [&](float (&kc)[20], uint32_t stg, int acc_in) {
    WG_FENCE();
#pragma unroll
    for (int s = 0; s < 8; s++) wgmma_ss_n40(kc, qdesc(stg + s * SLAB), qdesc(stg + s * SLAB + 2048), s ? 1 : acc_in);
    WG_COMMIT();
    WG_WAIT(0);
  };
  uint32_t eq[32];
  {
    uint4 af[4], aq[4], vp[4];
    float p[4][8];
#pragma unroll
    for (int u = 0; u < 4; u++) af[u] = pack8(acc[u >> 1] + 16 + 8 * (u & 1));
    feat(af, p);
#pragma unroll
    for (int u = 0; u < 4; u++) { aq[u] = pack8(acc[u >> 1] + 8 * (u & 1)); vp[u] = pack8(acc[u >> 1] + 32 + 8 * (u & 1)); }
    WG_WAIT(0);
    uint32_t pw[16], ek[32];
    packp(p, pw);
#pragma unroll
    for (int u = 0; u < 4; u++) dual_exp(pw + 4 * u, ek + 8 * u);
    TS(wg * 16 + 12);
    mbar_wait(BAR(MB_AUX));
    float rs[8][4];
    WG_FENCE();
#pragma unroll
    for (int i = 0; i < 8; i++) wgmma_rs_n8(rs[i], make_uint4(ek[4 * i], ek[4 * i + 1], ek[4 * i + 2], ek[4 * i + 3]), qdesc(sb + OFF_ONE), 0);
    WG_COMMIT();
    feat(aq, p);
    const uint32_t sl = (wg ? stg1 : stg0) + w * SLAB + lane * 16;
#pragma unroll
    for (int i = 0; i < 4; i++) stsm4(sl + (i >> 1) * 4 * SLAB + 2048 + (i & 1) * 512, vp[i].x, vp[i].y, vp[i].z, vp[i].w);
    sts128(sl + (lane >> 4) * (4 * SLAB - 256) + 3072, 0x3F803F80u, 0x3F803F80u, 0x3F803F80u, 0x3F803F80u);
    WG_WAIT(1);
#pragma unroll
    for (int i = 0; i < 8; i++) {
      normalise(ek + 4 * i, rs[i]);
      stsm4(sl + (i >> 2) * 4 * SLAB + (i & 3) * 512, ek[4 * i], ek[4 * i + 1], ek[4 * i + 2], ek[4 * i + 3]);
    }
    asm volatile("fence.proxy.async.shared::cta;" ::: "memory");
    TS(wg * 16 + 13);
    if (wg) {
      nb_arrive(NB_ST0, 256);
    } else {
      float kc[20];
      uint4* pp = g_part + (size_t)(hp * 8 + rt) * 144 + t;
      uint32_t* pz = (uint32_t*)(pp - t + 128) + w * 16 + c * 8 + g;
      asm volatile("" : "+l"(pp), "+l"(pz));
      nb_sync(NB_WG0, 128);
      contract(kc, stg0, 0);
      mbar_wait(BAR(MB_UFULL));
      TS(15);
      nb_sync(NB_ST0, 256);
      contract(kc, stg1, 1);
      TS(6);
      float kv[8];
#pragma unroll
      for (int i = 0; i < 8; i++) kv[i] = w & 2 ? kc[8 + i] : kc[i];
      st_x(pp, nz(pack_bf(kv[0], kv[1])), pack_bf(kv[2], kv[3]), pack_bf(kv[4], kv[5]), pack_bf(kv[6], kv[7]));
      if (c < 2) st_x32(pz, nz(fu(c ? kc[18] : kc[16])));
      TS(5);
    }
    SPLIT();
    WG_WAIT(0);
    packp(p, pw);
#pragma unroll
    for (int u = 0; u < 4; u++) dual_exp(pw + 4 * u, eq + 8 * u);
    SPLIT();
  }
  TS(wg * 16 + 4);
  if (wg == 1) {
    mbar_wait(BAR(MB_UFULL));
    const uint4* ps = g_part + (size_t)hp * 8 * 144 + t;
    const uint32_t* zs = (const uint32_t*)(g_part + (size_t)(hp * 8 + (lane >> 4) * 4) * 144 + 128) + w * 16 + (lane & 15);
    uint4 v[8];
    uint32_t zv[4];
#pragma unroll 1
    for (int it = 0; it < SPIN_MAX; it++) {
#pragma unroll
      for (int i = 0; i < 8; i++) v[i] = ld_x(ps + i * 144);
#pragma unroll
      for (int i = 0; i < 4; i++) zv[i] = ld_x32(zs + i * 576);
      uint32_t m = min(min(zv[0], zv[1]), min(zv[2], zv[3]));
#pragma unroll
      for (int i = 0; i < 8; i++) m = min(m, v[i].x);
      if (__all_sync(0xffffffffu, m != 0)) break;
    }
    float s[8];
    WG_FENCE();
#pragma unroll
    for (int r = 0; r < 8; r++) wgmma_rs_n16(s, v[r], qdesc(sb + OFF_EYE), r);
    WG_COMMIT();
    float zsum = (uf(zv[0]) + uf(zv[1])) + (uf(zv[2]) + uf(zv[3]));
    zsum += __shfl_xor_sync(0xffffffffu, zsum, 16);
    const uint32_t z1 = pack_bf(zsum, 1.f);
    if (lane < 16) sts128(kvs + w * 768 + 512 + lane * 16, z1, z1, z1, z1);
    WG_WAIT(0);
    stsm4(kvs + w * 768 + lane * 16, pack_bf(s[0], s[1]), pack_bf(s[2], s[3]), pack_bf(s[4], s[5]), pack_bf(s[6], s[7]));
    asm volatile("fence.proxy.async.shared::cta;" ::: "memory");
    TS(22);
  }
  nb_sync(NB_KV, 256);
  {
    float n[8][12];
    WG_FENCE();
#pragma unroll
    for (int i = 0; i < 8; i++) wgmma_rs_n24(n[i], make_uint4(eq[4 * i], eq[4 * i + 1], eq[4 * i + 2], eq[4 * i + 3]), qdesc(kvs + (i & 3) * 768), 0);
    WG_COMMIT();
    uint32_t* od = (uint32_t*)(g_o + (size_t)((rt * 4 + wg * 2) * 32 + hp * 2) * 128) + w * 64 + lane;
    WG_WAIT(0);
#pragma unroll
    for (int u = 0; u < 4; u++) {
      float(&np)[12] = n[2 * u];
      const float(&nm)[12] = n[2 * u + 1];
      const float q0 = np[9] * rcp(nm[9]), q1 = np[11] * rcp(nm[11]);
      const float r0 = rcp(fmaf(nm[8], q0, fmaf(np[9], 1e-6f, np[8]))), r1 = rcp(fmaf(nm[10], q1, fmaf(np[11], 1e-6f, np[10])));
#pragma unroll
      for (int i = 0; i < 8; i++) np[i] = fmaf(nm[i], (i & 2) ? q1 : q0, np[i]);
      uint32_t* o = od + (u >> 1) * 16384 + (u & 1) * 512;
      o[0] = pack_bf(np[0] * r0, np[1] * r0);
      o[32] = pack_bf(np[2] * r1, np[3] * r1);
      o[256] = pack_bf(np[4] * r0, np[5] * r0);
      o[288] = pack_bf(np[6] * r1, np[7] * r1);
      if (u == 1) SPLIT();
    }
  }
  TS(wg * 16 + 7);
  nb_arrive(NB_ODONE, 288);
  if (w == 3) {
    nb_sync(NB_OREL + wg, 128);
    if (lane == 0) asm volatile("red.release.gpu.global.add.u32 [%0], 1;" ::"l"((uint32_t*)(P.xs + X_CNT) + (8 + rt) * 32) : "memory");
    if (lane == 0) TS1(57);
    __syncwarp();
  } else {
    nb_arrive(NB_OREL + wg, 128);
  }
  if (wg) { if (w == 0) TSDUMP(16); return; }
  mbar_wait(BAR(MB_WO));
  mbar_wait(BAR(MB_OA));
  TS(8);
  nb_sync(NB_BDONE, 288);
  TS(9);
  float oc[64];
  {
    constexpr uint64_t ha = mkdesc(0, 0, 128, 0), hb = mkdesc(0, 0, 1024, 1);
    constexpr uint32_t da0 = (uint32_t)mkdesc(stg1, 1024, 0, 0), db0 = (uint32_t)mkdesc(sb + OFF_W, 8192, 0, 0);
#pragma unroll 1
    for (int j = 0; j < 8; j++) {
      const int kb = (j + 7) & 7;
      if ((j & 3) == 1) mbar_spin(j == 1 ? BAR(MB_OC) : BAR(MB_OB));
      WG_FENCE();
#pragma unroll
      for (int k = 0; k < 4; k++) wgmma_ss_n128(oc, ha | (da0 + 512 * kb + 128 * k), hb | (db0 + 1024 * kb + 128 * k), k ? 1 : j);
      WG_COMMIT();
    }
    WG_WAIT(0);
  }
  TS(10);
  const uint32_t ot = ((sb + OFF_T + 1023) & ~1023u) + w * 4096;
#pragma unroll
  for (int hf = 0; hf < 2; hf++) {
#pragma unroll
    for (int i = 8 * hf; i < 8 * hf + 8; i += 2)
      stsm4(ot + hf * 2048 + (lane & 15) * 128 + (((i + (lane >> 4)) ^ lane) & 7) * 16, pack_bf(oc[4 * i], oc[4 * i + 1]),
            pack_bf(oc[4 * i + 2], oc[4 * i + 3]), pack_bf(oc[4 * i + 4], oc[4 * i + 5]), pack_bf(oc[4 * i + 6], oc[4 * i + 7]));
    asm volatile("fence.proxy.async.shared::cta;" ::: "memory");
    __syncwarp();
    e_store2d(&mout, ot + hf * 2048, (hp & 3) * 128 + hf * 64, (rt * 4 + (hp >> 2)) * 64 + w * 16);
  }
  asm volatile(ELECT "cp.async.bulk.commit_group;\n@p cp.async.bulk.wait_group.read 0;\n}\n" ::: "memory");
  TS(wg * 16 + 11);
  GT(61 + wg);
  if (w == 0) TSDUMP(0);
  if (w == 1) TSDUMP(48);
}

typedef CUresult (*EncodeFn)(CUtensorMap*, CUtensorMapDataType, cuuint32_t, void*, const cuuint64_t*, const cuuint64_t*,
                             const cuuint32_t*, const cuuint32_t*, CUtensorMapInterleave, CUtensorMapSwizzle,
                             CUtensorMapL2promotion, CUtensorMapFloatOOBfill);

}

extern "C" void kernel_launch(void* const* d_in, const int* in_sizes, int n_in, void* d_out, int out_size) {
  (void)in_sizes; (void)n_in; (void)out_size;
  void* fn = nullptr;
  cudaDriverEntryPointQueryResult qr;
  cudaGetDriverEntryPoint("cuTensorMapEncodeTiled", &fn, cudaEnableDefault, &qr);
  EncodeFn enc = (EncodeFn)fn;
  CUtensorMap mx, mw, mo, mu, mout, mw4;
  const cuuint32_t es[5] = {1, 1, 1, 1, 1};
  {
    cuuint64_t dims[2] = {512, 2048}, st[1] = {1024};
    cuuint32_t box[2] = {64, 128};
    enc(&mx, CU_TENSOR_MAP_DATA_TYPE_BFLOAT16, 2, d_in[0], dims, st, box, es, CU_TENSOR_MAP_INTERLEAVE_NONE,
        CU_TENSOR_MAP_SWIZZLE_128B, CU_TENSOR_MAP_L2_PROMOTION_L2_128B, CU_TENSOR_MAP_FLOAT_OOB_FILL_NONE);
  }
  {
    cuuint64_t dims[3] = {512, 512, 3}, st[2] = {3072, 1024};
    cuuint32_t box[3] = {32, 64, 3};
    enc(&mw, CU_TENSOR_MAP_DATA_TYPE_BFLOAT16, 3, d_in[1], dims, st, box, es, CU_TENSOR_MAP_INTERLEAVE_NONE,
        CU_TENSOR_MAP_SWIZZLE_64B, CU_TENSOR_MAP_L2_PROMOTION_L2_128B, CU_TENSOR_MAP_FLOAT_OOB_FILL_NONE);
  }
  {
    cuuint64_t dims[3] = {64, 512, 8}, st[2] = {1024, 128};
    cuuint32_t box[3] = {64, 64, 2};
    enc(&mo, CU_TENSOR_MAP_DATA_TYPE_BFLOAT16, 3, d_in[3], dims, st, box, es, CU_TENSOR_MAP_INTERLEAVE_NONE,
        CU_TENSOR_MAP_SWIZZLE_128B, CU_TENSOR_MAP_L2_PROMOTION_L2_128B, CU_TENSOR_MAP_FLOAT_OOB_FILL_NONE);
  }
  {
    cuuint64_t dims[4] = {512, 4, 16, 32}, st[3] = {16384, 1024, 65536};
    cuuint32_t box[4] = {64, 4, 16, 2};
    enc(&mu, CU_TENSOR_MAP_DATA_TYPE_BFLOAT16, 4, d_in[4], dims, st, box, es, CU_TENSOR_MAP_INTERLEAVE_NONE,
        CU_TENSOR_MAP_SWIZZLE_128B, CU_TENSOR_MAP_L2_PROMOTION_L2_128B, CU_TENSOR_MAP_FLOAT_OOB_FILL_NONE);
  }
  {
    cuuint64_t dims[2] = {1024, 2048}, st[1] = {2048};
    cuuint32_t box[2] = {64, 16};
    enc(&mout, CU_TENSOR_MAP_DATA_TYPE_BFLOAT16, 2, d_out, dims, st, box, es, CU_TENSOR_MAP_INTERLEAVE_NONE,
        CU_TENSOR_MAP_SWIZZLE_128B, CU_TENSOR_MAP_L2_PROMOTION_NONE, CU_TENSOR_MAP_FLOAT_OOB_FILL_NONE);
  }
  {
    cuuint64_t dims[4] = {512, 64, 3, 8}, st[3] = {3072, 1024, 64 * 3072};
    cuuint32_t box[4] = {32, 64, 3, 4};
    enc(&mw4, CU_TENSOR_MAP_DATA_TYPE_BFLOAT16, 4, d_in[1], dims, st, box, es, CU_TENSOR_MAP_INTERLEAVE_NONE,
        CU_TENSOR_MAP_SWIZZLE_64B, CU_TENSOR_MAP_L2_PROMOTION_L2_128B, CU_TENSOR_MAP_FLOAT_OOB_FILL_NONE);
  }
  Params P;
  P.x = (const __nv_bfloat16*)d_in[0];
  P.wphi = (const __nv_bfloat16*)d_in[2];
  P.wo = (const __nv_bfloat16*)d_in[3];
  P.logA = (const __nv_bfloat16*)d_in[5];
  P.Aim = (const __nv_bfloat16*)d_in[6];
  P.Cre = (const __nv_bfloat16*)d_in[7];
  P.Cim = (const __nv_bfloat16*)d_in[8];
  P.logdt = (const __nv_bfloat16*)d_in[9];
  P.Dskip = (const __nv_bfloat16*)d_in[10];
  P.out = (__nv_bfloat16*)d_out;
  cudaGetSymbolAddress((void**)&P.xs, g_x);
  P.ts = nullptr;
  cudaFuncSetAttribute(fused_kernel, cudaFuncAttributeMaxDynamicSharedMemorySize, SMEM_BYTES);
  fused_kernel<<<NCTA, NTHREADS, SMEM_BYTES>>>(P, mx, mw, mo, mu, mout, mw4);
}
```

```cpp
#include <cuda_runtime.h>
#include <cuda_bf16.h>
#include <cuda_fp16.h>
#include <cuda.h>
#include <stdint.h>

#define DBG_TS 0

namespace {

constexpr int NTHREADS = 512;
constexpr int NCTA = 128;
constexpr int OFF_W = 0;
constexpr int OFF_X = 98304;
constexpr int OFF_U = OFF_X + 65536;
constexpr int U_CH = 4416, U_ODD = 2240, U_PAD = 128;
constexpr int OFF_STG0 = OFF_U + 18432;
constexpr int SLAB = 3328;
constexpr int OFF_T = OFF_STG0 + 8 * SLAB;
constexpr int T_CH = 5216;
constexpr int T_D = 0;
constexpr int T_5 = 2144;
constexpr int T_3 = T_5 + 384;
constexpr int T_7 = T_5 + 1024;
constexpr int T_9 = T_7 + 320;
constexpr int T_KC = T_9 + 320;
constexpr int T_ST = T_5 - 1024;
constexpr int OFF_PHI = OFF_T + 4 * T_CH;
constexpr int OFF_EYE = OFF_PHI + 1024, OFF_ONE = OFF_EYE + 512;
constexpr int OFF_BAR = OFF_ONE + 256;
constexpr int SMEM_BYTES = OFF_BAR + 512 + 256 * DBG_TS;
constexpr uint32_t SB = 1024;
static_assert(T_KC + 2 * 656 <= T_CH, "table size");
static_assert(SMEM_BYTES <= 232448, "smem");
constexpr int MB_URAW = 0, MB_FULL = 1  , MB_WO = 17, MB_UFULL = 18, MB_OA = 19, MB_OB = 20, MB_OC = 21,
              MB_EMPTY = 22  , MB_AUX = 38;
__host__ __device__ constexpr uint32_t BAR(int i) { return SB + OFF_BAR + 8 * i; }
constexpr int NB_WG0 = 1, NB_ODONE = 2, NB_ST0 = 3  , NB_KV = 5, NB_YZ = 6, NB_INIT = 7, NB_PREP = 8, NB_PROD = 9, NB_KREAD = 10, NB_BDONE = 11;
#define X2_AT -1
#define U_AT 2
#define ZERO_STEP 12
constexpr int SPIN_MAX = 1 << 16;

constexpr int X_CNT = 0;
constexpr int X_PART = 256;
constexpr int X_O = X_PART + 16 * 8 * 144;
constexpr int X_Y = X_O + 32 * 32 * 128;
constexpr int X_UT = X_Y + 512 * 8 * 32;
constexpr int X_SIZE = X_UT + 512 * (U_CH / 16);
__device__ __align__(128) uint4 g_x[X_SIZE];
extern __shared__ uint8_t smem_raw[];
#define TS(i) do {} while (0)
#define TS1(i) do {} while (0)
#define GT(i) do {} while (0)
#define TSDUMP(base) do {} while (0)

__device__ __forceinline__ uint32_t smem_u32(const void* p) { return (uint32_t)__cvta_generic_to_shared(p); }
__device__ __forceinline__ void mbar_arrive(uint32_t b) {
  asm volatile("mbarrier.arrive.shared::cta.b64 _, [%0];" ::"r"(b) : "memory");
}
__device__ __forceinline__ void mbar_wait(uint32_t b) {
  uint32_t done = 0;
#pragma unroll 1
  for (int i = 0; i < SPIN_MAX && !done; i++) {
    asm volatile("{\n.reg .pred p;\nmbarrier.try_wait.parity.shared::cta.b64 p, [%1], 0, 4000;\nselp.u32 %0, 1, 0, p;\n}\n"
                 : "=r"(done) : "r"(b) : "memory");
  }
}
__device__ __forceinline__ void mbar_spin(uint32_t b) {
  uint32_t done = 0;
#pragma unroll 1
  for (int i = 0; i < (SPIN_MAX << 4) && !done; i++) {
    asm volatile("{\n.reg .pred p;\nmbarrier.try_wait.parity.shared::cta.b64 p, [%1], 0;\nselp.u32 %0, 1, 0, p;\n}\n"
                 : "=r"(done) : "r"(b) : "memory");
  }
}
__device__ __forceinline__ void mbar_init(uint32_t b, int n) {
  asm volatile("mbarrier.init.shared::cta.b64 [%0], %1;" ::"r"(b), "r"(n) : "memory");
}
__device__ __forceinline__ void mbar_expect(uint32_t b, int bytes) {
  asm volatile("mbarrier.arrive.expect_tx.shared::cta.b64 _, [%0], %1;" ::"r"(b), "r"(bytes) : "memory");
}
__device__ __forceinline__ void nb_sync(int id, int n) { asm volatile("bar.sync %0, %1;" ::"r"(id), "r"(n) : "memory"); }
__device__ __forceinline__ void nb_arrive(int id, int n) { asm volatile("bar.arrive %0, %1;" ::"r"(id), "r"(n) : "memory"); }
#define ELECT "{\n.reg .pred p;\nelect.sync _|p, 0xffffffff;\n@p "
__device__ __forceinline__ void e_arrive(uint32_t b) {
  asm volatile(ELECT "mbarrier.arrive.shared::cta.b64 _, [%0];\n}\n" ::"r"(b) : "memory");
}
__device__ __forceinline__ void e_expect(uint32_t b, int bytes) {
  asm volatile(ELECT "mbarrier.arrive.expect_tx.shared::cta.b64 _, [%0], %1;\n}\n" ::"r"(b), "r"(bytes) : "memory");
}
__device__ __forceinline__ void e_tma2d(uint32_t dst, const CUtensorMap* m, uint32_t bar, int c0, int c1) {
  asm volatile(ELECT "cp.async.bulk.tensor.2d.shared::cluster.global.mbarrier::complete_tx::bytes [%0], [%1, {%3,%4}], [%2];\n}\n"
               ::"r"(dst), "l"(m), "r"(bar), "r"(c0), "r"(c1) : "memory");
}
__device__ __forceinline__ void e_tma3d(uint32_t dst, const CUtensorMap* m, uint32_t bar, int c0, int c1, int c2) {
  asm volatile(ELECT "cp.async.bulk.tensor.3d.shared::cluster.global.mbarrier::complete_tx::bytes [%0], [%1, {%3,%4,%5}], [%2];\n}\n"
               ::"r"(dst), "l"(m), "r"(bar), "r"(c0), "r"(c1), "r"(c2) : "memory");
}
__device__ __forceinline__ void e_tma4d(uint32_t dst, const CUtensorMap* m, uint32_t bar, int c0, int c3) {
  asm volatile(ELECT "cp.async.bulk.tensor.4d.shared::cluster.global.mbarrier::complete_tx::bytes [%0], [%1, {%3,%5,%5,%4}], [%2];\n}\n"
               ::"r"(dst), "l"(m), "r"(bar), "r"(c0), "r"(c3), "r"(0) : "memory");
}
__device__ __forceinline__ void e_bulk(uint32_t dst, const void* src, int bytes, uint32_t bar) {
  asm volatile(ELECT "cp.async.bulk.shared::cluster.global.mbarrier::complete_tx::bytes [%0], [%1], %2, [%3];\n}\n"
               ::"r"(dst), "l"(src), "r"(bytes), "r"(bar) : "memory");
}
__device__ __forceinline__ void e_prefetch(const void* p, int bytes) {
  asm volatile(ELECT "cp.async.bulk.prefetch.L2.global [%0], %1;\n}\n" ::"l"(p), "r"(bytes) : "memory");
}
__device__ __forceinline__ void e_store2d(const CUtensorMap* m, uint32_t src, int c0, int c1) {
  asm volatile(ELECT "cp.async.bulk.tensor.2d.global.shared::cta.bulk_group [%0, {%2,%3}], [%1];\n}\n"
               ::"l"(m), "r"(src), "r"(c0), "r"(c1) : "memory");
}
__host__ __device__ constexpr uint64_t mkdesc(uint32_t addr, uint32_t lbo, uint32_t sbo, int swz) {
  return (uint64_t)((addr & 0x3FFFF) >> 4) | ((uint64_t)(lbo >> 4) << 16) | ((uint64_t)(sbo >> 4) << 32) |
         ((uint64_t)swz << 62);
}
#define SPLIT() asm volatile("{\n.reg .pred p;\nsetp.eq.u32 p, %0, %1;\n@p exit;\n}\n" ::"r"(blockIdx.y), "n"(__LINE__) : "memory")
#define WG_FENCE() asm volatile("wgmma.fence.sync.aligned;" ::: "memory")
#define WG_COMMIT() asm volatile("wgmma.commit_group.sync.aligned;" ::: "memory")
#define WG_WAIT(n) asm volatile("wgmma.wait_group.sync.aligned " #n ";" ::: "memory")

__device__ __forceinline__ void mma(float& d0, float& d1, float& d2, float& d3, uint32_t a0, uint32_t a1, uint32_t a2,
                                    uint32_t a3, uint32_t b0, uint32_t b1) {
  asm volatile("mma.sync.aligned.m16n8k16.row.col.f32.bf16.bf16.f32 {%0,%1,%2,%3},{%4,%5,%6,%7},{%8,%9},{%0,%1,%2,%3};"
               : "+f"(d0), "+f"(d1), "+f"(d2), "+f"(d3)
               : "r"(a0), "r"(a1), "r"(a2), "r"(a3), "r"(b0), "r"(b1));
}
__device__ __forceinline__ void mmac(float (&d)[4], uint32_t a0, uint32_t a1, uint32_t a2, uint32_t a3, uint32_t b0,
                                     uint32_t b1, const float (&c)[4]) {
  asm volatile("mma.sync.aligned.m16n8k16.row.col.f32.bf16.bf16.f32 {%0,%1,%2,%3},{%4,%5,%6,%7},{%8,%9},{%10,%11,%12,%13};"
               : "=f"(d[0]), "=f"(d[1]), "=f"(d[2]), "=f"(d[3])
               : "r"(a0), "r"(a1), "r"(a2), "r"(a3), "r"(b0), "r"(b1), "f"(c[0]), "f"(c[1]), "f"(c[2]), "f"(c[3]));
}
__device__ __forceinline__ void mma_p(int p, float (&d)[4], uint32_t a0, uint32_t a1, uint32_t a2, uint32_t a3, uint32_t b0, uint32_t b1) {
  asm volatile("{\n.reg .pred q;\nsetp.ne.b32 q, %10, 0;\n"
               "@q mma.sync.aligned.m16n8k16.row.col.f32.bf16.bf16.f32 {%0,%1,%2,%3},{%4,%5,%6,%7},{%8,%9},{%0,%1,%2,%3};\n}\n"
               : "+f"(d[0]), "+f"(d[1]), "+f"(d[2]), "+f"(d[3])
               : "r"(a0), "r"(a1), "r"(a2), "r"(a3), "r"(b0), "r"(b1), "r"(p));
}
__device__ __forceinline__ void mmac_p(int p, float (&d)[4], uint32_t a0, uint32_t a1, uint32_t a2, uint32_t a3, uint32_t b0,
                                       uint32_t b1, const float (&c)[4]) {
  asm volatile("{\n.reg .pred q;\nsetp.ne.b32 q, %14, 0;\n"
               "@q mma.sync.aligned.m16n8k16.row.col.f32.bf16.bf16.f32 {%0,%1,%2,%3},{%4,%5,%6,%7},{%8,%9},{%10,%11,%12,%13};\n}\n"
               : "+f"(d[0]), "+f"(d[1]), "+f"(d[2]), "+f"(d[3])
               : "r"(a0), "r"(a1), "r"(a2), "r"(a3), "r"(b0), "r"(b1), "f"(c[0]), "f"(c[1]), "f"(c[2]), "f"(c[3]), "r"(p));
}
__device__ __forceinline__ void mma_h(float (&d)[4], const uint32_t (&a)[4], uint32_t b0, uint32_t b1) {
  asm volatile("mma.sync.aligned.m16n8k16.row.col.f32.f16.f16.f32 {%0,%1,%2,%3},{%4,%5,%6,%7},{%8,%9},{%0,%1,%2,%3};"
               : "+f"(d[0]), "+f"(d[1]), "+f"(d[2]), "+f"(d[3]) : "r"(a[0]), "r"(a[1]), "r"(a[2]), "r"(a[3]), "r"(b0), "r"(b1));
}
__device__ __forceinline__ void mma0(float& d0, float& d1, float& d2, float& d3, uint32_t a0, uint32_t a1, uint32_t a2,
                                     uint32_t a3, uint32_t b0, uint32_t b1) {
  asm volatile("mma.sync.aligned.m16n8k16.row.col.f32.bf16.bf16.f32 {%0,%1,%2,%3},{%4,%5,%6,%7},{%8,%9},{%10,%10,%10,%10};"
               : "=f"(d0), "=f"(d1), "=f"(d2), "=f"(d3)
               : "r"(a0), "r"(a1), "r"(a2), "r"(a3), "r"(b0), "r"(b1), "f"(0.f));
}
__device__ __forceinline__ uint32_t pack_bf(float lo, float hi) {
  uint32_t r;
  asm("cvt.rn.bf16x2.f32 %0, %1, %2;" : "=r"(r) : "f"(hi), "f"(lo));
  return r;
}
__device__ __forceinline__ float bf_lo(uint32_t w) { return __uint_as_float(w << 16); }
__device__ __forceinline__ float bf_hi(uint32_t w) { return __uint_as_float(w & 0xffff0000u); }
__device__ __forceinline__ float bf_round(float x) { return __bfloat162float(__float2bfloat16_rn(x)); }
__device__ __forceinline__ uint32_t bmax2(uint32_t a, uint32_t b) {
  uint32_t r; asm("max.bf16x2 %0, %1, %2;" : "=r"(r) : "r"(a), "r"(b)); return r;
}
__device__ __forceinline__ uint32_t bmin2(uint32_t a, uint32_t b) {
  uint32_t r; asm("min.bf16x2 %0, %1, %2;" : "=r"(r) : "r"(a), "r"(b)); return r;
}
__device__ __forceinline__ float ex2(float x) { float r; asm("ex2.approx.ftz.f32 %0, %1;" : "=f"(r) : "f"(x)); return r; }
__device__ __forceinline__ float rcp(float x) { float r; asm("rcp.approx.ftz.f32 %0, %1;" : "=f"(r) : "f"(x)); return r; }
__device__ __forceinline__ void ldsm4(uint32_t (&r)[4], uint32_t a) {
  asm volatile("ldmatrix.sync.aligned.m8n8.x4.shared.b16 {%0,%1,%2,%3}, [%4];"
               : "=r"(r[0]), "=r"(r[1]), "=r"(r[2]), "=r"(r[3]) : "r"(a) : "memory");
}
__device__ __forceinline__ void ldsm4t(uint32_t (&r)[4], uint32_t a) {
  asm volatile("ldmatrix.sync.aligned.m8n8.x4.trans.shared.b16 {%0,%1,%2,%3}, [%4];"
               : "=r"(r[0]), "=r"(r[1]), "=r"(r[2]), "=r"(r[3]) : "r"(a) : "memory");
}
__device__ __forceinline__ void stsm4(uint32_t a, uint32_t r0, uint32_t r1, uint32_t r2, uint32_t r3) {
  asm volatile("stmatrix.sync.aligned.m8n8.x4.shared.b16 [%0], {%1,%2,%3,%4};"
               ::"r"(a), "r"(r0), "r"(r1), "r"(r2), "r"(r3) : "memory");
}
__device__ __forceinline__ uint32_t lds32(uint32_t a) {
  uint32_t r; asm volatile("ld.shared.u32 %0, [%1];" : "=r"(r) : "r"(a) : "memory"); return r;
}
__device__ __forceinline__ uint32_t lds16(uint32_t a) {
  uint32_t r; asm volatile("{\n.reg .u16 h;\nld.shared.u16 h, [%1];\ncvt.u32.u16 %0, h;\n}\n" : "=r"(r) : "r"(a) : "memory"); return r;
}
__device__ __forceinline__ uint2 lds64(uint32_t a) {
  uint2 r; asm volatile("ld.shared.v2.u32 {%0,%1}, [%2];" : "=r"(r.x), "=r"(r.y) : "r"(a) : "memory"); return r;
}
__device__ __forceinline__ uint4 lds128(uint32_t a) {
  uint4 r;
  asm volatile("ld.shared.v4.u32 {%0,%1,%2,%3}, [%4];" : "=r"(r.x), "=r"(r.y), "=r"(r.z), "=r"(r.w) : "r"(a) : "memory");
  return r;
}
__device__ __forceinline__ void sts32(uint32_t a, uint32_t v) { asm volatile("st.shared.u32 [%0], %1;" ::"r"(a), "r"(v) : "memory"); }
__device__ __forceinline__ void sts16(uint32_t a, uint32_t v) {
  asm volatile("{\n.reg .u16 h;\ncvt.u16.u32 h, %1;\nst.shared.u16 [%0], h;\n}\n" ::"r"(a), "r"(v) : "memory");
}
__device__ __forceinline__ void sts64(uint32_t a, uint32_t x, uint32_t y) {
  asm volatile("st.shared.v2.u32 [%0], {%1,%2};" ::"r"(a), "r"(x), "r"(y) : "memory");
}
__device__ __forceinline__ void sts128(uint32_t a, uint32_t x, uint32_t y, uint32_t z, uint32_t w) {
  asm volatile("st.shared.v4.u32 [%0], {%1,%2,%3,%4};" ::"r"(a), "r"(x), "r"(y), "r"(z), "r"(w) : "memory");
}
__device__ __forceinline__ uint4 ld_x(const uint4* p) {
  uint4 r;
  asm volatile("{\n.reg .b128 t;\nld.relaxed.gpu.global.b128 t, [%4];\nmov.b128 {%0,%1,%2,%3}, t;\n}\n"
               : "=r"(r.x), "=r"(r.y), "=r"(r.z), "=r"(r.w) : "l"(p) : "memory");
  return r;
}
__device__ __forceinline__ uint32_t ld_x32(const uint32_t* p) {
  uint32_t r; asm volatile("ld.relaxed.gpu.global.u32 %0, [%1];" : "=r"(r) : "l"(p) : "memory"); return r;
}
__device__ __forceinline__ void st_x(uint4* p, uint32_t x, uint32_t y, uint32_t z, uint32_t w) {
  asm volatile("{\n.reg .b128 t;\nmov.b128 t, {%1,%2,%3,%4};\nst.relaxed.gpu.global.b128 [%0], t;\n}\n"
               ::"l"(p), "r"(x), "r"(y), "r"(z), "r"(w) : "memory");
}
__device__ __forceinline__ void st_x_p(int p, uint4* a, uint32_t x, uint32_t y, uint32_t z, uint32_t w) {
  asm volatile("{\n.reg .b128 t;\n.reg .pred q;\nsetp.ne.b32 q, %5, 0;\nmov.b128 t, {%1,%2,%3,%4};\n@q st.relaxed.gpu.global.b128 [%0], t;\n}\n"
               ::"l"(a), "r"(x), "r"(y), "r"(z), "r"(w), "r"(p) : "memory");
}
__device__ __forceinline__ void sts64_p(int p, uint32_t a, uint32_t x, uint32_t y) {
  asm volatile("{\n.reg .pred q;\nsetp.ne.b32 q, %3, 0;\n@q st.shared.v2.u32 [%0], {%1,%2};\n}\n" ::"r"(a), "r"(x), "r"(y), "r"(p) : "memory");
}
__device__ __forceinline__ void st_x32(uint32_t* p, uint32_t x) {
  asm volatile("st.relaxed.gpu.global.u32 [%0], %1;" ::"l"(p), "r"(x) : "memory");
}
__device__ __forceinline__ uint32_t nz(uint32_t w) { return max(w, 1u); }
__device__ __forceinline__ uint32_t fu(float x) { return __float_as_uint(x); }
__device__ __forceinline__ float uf(uint32_t x) { return __uint_as_float(x); }

__device__ __forceinline__ void wgmma_ss_n96(float (&d)[48], uint64_t da, uint64_t db, int sc) {
  asm volatile("{\n.reg .pred p;\nsetp.ne.b32 p, %50, 0;\n"
      "wgmma.mma_async.sync.aligned.m64n96k16.f32.bf16.bf16 "
      "{%0,%1,%2,%3,%4,%5,%6,%7,%8,%9,%10,%11,%12,%13,%14,%15,%16,%17,%18,%19,%20,%21,%22,%23,%24,%25,%26,%27,%28,%29,%30,%31,%32,%33,%34,%35,%36,%37,%38,%39,%40,%41,%42,%43,%44,%45,%46,%47}, "
      "%48, %49, p, 1, 1, 0, 1;\n}\n"
      : "+f"(d[0]), "+f"(d[1]), "+f"(d[2]), "+f"(d[3]), "+f"(d[4]), "+f"(d[5]), "+f"(d[6]), "+f"(d[7]),
        "+f"(d[8]), "+f"(d[9]), "+f"(d[10]), "+f"(d[11]), "+f"(d[12]), "+f"(d[13]), "+f"(d[14]), "+f"(d[15]),
        "+f"(d[16]), "+f"(d[17]), "+f"(d[18]), "+f"(d[19]), "+f"(d[20]), "+f"(d[21]), "+f"(d[22]), "+f"(d[23]),
        "+f"(d[24]), "+f"(d[25]), "+f"(d[26]), "+f"(d[27]), "+f"(d[28]), "+f"(d[29]), "+f"(d[30]), "+f"(d[31]),
        "+f"(d[32]), "+f"(d[33]), "+f"(d[34]), "+f"(d[35]), "+f"(d[36]), "+f"(d[37]), "+f"(d[38]), "+f"(d[39]),
        "+f"(d[40]), "+f"(d[41]), "+f"(d[42]), "+f"(d[43]), "+f"(d[44]), "+f"(d[45]), "+f"(d[46]), "+f"(d[47])
      : "l"(da), "l"(db), "r"(sc));
}

__device__ __forceinline__ void wgmma_ss_n128(float (&d)[64], uint64_t da, uint64_t db, int sc) {
  asm volatile("{\n.reg .pred p;\nsetp.ne.b32 p, %66, 0;\n"
      "wgmma.mma_async.sync.aligned.m64n128k16.f32.bf16.bf16 "
      "{%0,%1,%2,%3,%4,%5,%6,%7,%8,%9,%10,%11,%12,%13,%14,%15,%16,%17,%18,%19,%20,%21,%22,%23,%24,%25,%26,%27,%28,%29,%30,%31,%32,%33,%34,%35,%36,%37,%38,%39,%40,%41,%42,%43,%44,%45,%46,%47,%48,%49,%50,%51,%52,%53,%54,%55,%56,%57,%58,%59,%60,%61,%62,%63}, "
      "%64, %65, p, 1, 1, 0, 1;\n}\n"
      : "+f"(d[0]), "+f"(d[1]), "+f"(d[2]), "+f"(d[3]), "+f"(d[4]), "+f"(d[5]), "+f"(d[6]), "+f"(d[7]),
        "+f"(d[8]), "+f"(d[9]), "+f"(d[10]), "+f"(d[11]), "+f"(d[12]), "+f"(d[13]), "+f"(d[14]), "+f"(d[15]),
        "+f"(d[16]), "+f"(d[17]), "+f"(d[18]), "+f"(d[19]), "+f"(d[20]), "+f"(d[21]), "+f"(d[22]), "+f"(d[23]),
        "+f"(d[24]), "+f"(d[25]), "+f"(d[26]), "+f"(d[27]), "+f"(d[28]), "+f"(d[29]), "+f"(d[30]), "+f"(d[31]),
        "+f"(d[32]), "+f"(d[33]), "+f"(d[34]), "+f"(d[35]), "+f"(d[36]), "+f"(d[37]), "+f"(d[38]), "+f"(d[39]),
        "+f"(d[40]), "+f"(d[41]), "+f"(d[42]), "+f"(d[43]), "+f"(d[44]), "+f"(d[45]), "+f"(d[46]), "+f"(d[47]),
        "+f"(d[48]), "+f"(d[49]), "+f"(d[50]), "+f"(d[51]), "+f"(d[52]), "+f"(d[53]), "+f"(d[54]), "+f"(d[55]),
        "+f"(d[56]), "+f"(d[57]), "+f"(d[58]), "+f"(d[59]), "+f"(d[60]), "+f"(d[61]), "+f"(d[62]), "+f"(d[63])
      : "l"(da), "l"(db), "r"(sc));
}

__device__ __forceinline__ void wgmma_ss_n40(float (&d)[20], uint64_t da, uint64_t db, int sc) {
  asm volatile("{\n.reg .pred p;\nsetp.ne.b32 p, %22, 0;\n"
      "wgmma.mma_async.sync.aligned.m64n40k16.f32.bf16.bf16 "
      "{%0,%1,%2,%3,%4,%5,%6,%7,%8,%9,%10,%11,%12,%13,%14,%15,%16,%17,%18,%19}, "
      "%20, %21, p, 1, 1, 1, 1;\n}\n"
      : "+f"(d[0]), "+f"(d[1]), "+f"(d[2]), "+f"(d[3]), "+f"(d[4]), "+f"(d[5]), "+f"(d[6]), "+f"(d[7]),
        "+f"(d[8]), "+f"(d[9]), "+f"(d[10]), "+f"(d[11]), "+f"(d[12]), "+f"(d[13]), "+f"(d[14]), "+f"(d[15]),
        "+f"(d[16]), "+f"(d[17]), "+f"(d[18]), "+f"(d[19])
      : "l"(da), "l"(db), "r"(sc));
}

__device__ __forceinline__ void wgmma_rs_n8(float (&d)[4], const uint4& a, uint64_t db, int sc) {
  asm volatile("{\n.reg .pred p;\nsetp.ne.b32 p, %9, 0;\n"
      "wgmma.mma_async.sync.aligned.m64n8k16.f32.bf16.bf16 "
      "{%0,%1,%2,%3}, "
      "{%4,%5,%6,%7}, %8, p, 1, 1, 1;\n}\n"
      : "+f"(d[0]), "+f"(d[1]), "+f"(d[2]), "+f"(d[3])
      : "r"(a.x), "r"(a.y), "r"(a.z), "r"(a.w), "l"(db), "r"(sc));
}

__device__ __forceinline__ void wgmma_rs_n16(float (&d)[8], const uint4& a, uint64_t db, int sc) {
  asm volatile("{\n.reg .pred p;\nsetp.ne.b32 p, %13, 0;\n"
      "wgmma.mma_async.sync.aligned.m64n16k16.f32.bf16.bf16 "
      "{%0,%1,%2,%3,%4,%5,%6,%7}, "
      "{%8,%9,%10,%11}, %12, p, 1, 1, 1;\n}\n"
      : "+f"(d[0]), "+f"(d[1]), "+f"(d[2]), "+f"(d[3]), "+f"(d[4]), "+f"(d[5]), "+f"(d[6]), "+f"(d[7])
      : "r"(a.x), "r"(a.y), "r"(a.z), "r"(a.w), "l"(db), "r"(sc));
}

__device__ __forceinline__ void wgmma_rs_n24(float (&d)[12], const uint4& a, uint64_t db, int sc) {
  asm volatile("{\n.reg .pred p;\nsetp.ne.b32 p, %17, 0;\n"
      "wgmma.mma_async.sync.aligned.m64n24k16.f32.bf16.bf16 "
      "{%0,%1,%2,%3,%4,%5,%6,%7,%8,%9,%10,%11}, "
      "{%12,%13,%14,%15}, %16, p, 1, 1, 1;\n}\n"
      : "+f"(d[0]), "+f"(d[1]), "+f"(d[2]), "+f"(d[3]), "+f"(d[4]), "+f"(d[5]), "+f"(d[6]), "+f"(d[7]),
        "+f"(d[8]), "+f"(d[9]), "+f"(d[10]), "+f"(d[11])
      : "r"(a.x), "r"(a.y), "r"(a.z), "r"(a.w), "l"(db), "r"(sc));
}

struct Params {
  const __nv_bfloat16 *logA, *Aim, *Cre, *Cim, *logdt, *Dskip, *x, *wphi, *wo;
  __nv_bfloat16* out;
  uint4* xs;
  long long* ts;
};

__device__ __forceinline__ uint4 tr_row(const uint4 (&v)[8], int i) {
  uint32_t o[4];
#pragma unroll
  for (int m = 0; m < 4; m++) {
    const uint4 &ra = v[2 * m], &rb = v[2 * m + 1];
    const int k = i >> 1;
    const uint32_t xa = k == 0 ? ra.x : k == 1 ? ra.y : k == 2 ? ra.z : ra.w;
    const uint32_t xb = k == 0 ? rb.x : k == 1 ? rb.y : k == 2 ? rb.z : rb.w;
    o[m] = __byte_perm(xa, xb, (i & 1) ? 0x7632 : 0x5410);
  }
  return make_uint4(o[0], o[1], o[2], o[3]);
}

struct cpx { float r, i; };
__device__ __forceinline__ cpx csq(cpx a) { return {a.r * a.r - a.i * a.i, 2.f * (a.r * a.i)}; }
__device__ __forceinline__ cpx polar(float e, float t) {
  const float m = ex2(e);
  return {m * __cosf(t), m * __sinf(t)};
}

struct KgenRaw { unsigned short la, ai, cr, ci, ldt; };
__device__ __forceinline__ KgenRaw kgen_load(const Params& P, int d, int unit, int lane) {
  const int o = d * 128 + unit * 32 + lane;
  return {__ldg((const unsigned short*)P.logA + o), __ldg((const unsigned short*)P.Aim + o), __ldg((const unsigned short*)P.Cre + o),
          __ldg((const unsigned short*)P.Cim + o), __ldg((const unsigned short*)P.logdt + d)};
}
struct hmul { __half2 a, b; };
__device__ __forceinline__ hmul mk_mul(cpx w) {
  uint32_t b;
  asm("{\n.reg .f32 n;\nneg.ftz.f32 n, %1;\ncvt.rn.f16x2.f32 %0, %2, n;\n}\n" : "=r"(b) : "f"(w.i), "f"(w.r));
  return {__floats2half2_rn(w.r, w.i), *(const __half2*)&b};
}
__device__ __forceinline__ __half2 hcm(__half2 z, const hmul& w) { return __hfma2(__high2half2(z), w.b, __hmul2(__low2half2(z), w.a)); }
__device__ __forceinline__ uint32_t hu(__half2 v) { return *(const uint32_t*)&v; }

struct KgenAddr { uint32_t sa, sb, lb, lc, la; };
__device__ __forceinline__ KgenAddr kgen_addr(int lane, uint32_t buf) {
  KgenAddr a;
  a.sa = buf + (lane & 7) * 128 + ((((lane >> 3) ^ lane) & 7) << 4);
  a.lb = buf + (lane >> 3) * 128 + (((lane ^ (lane >> 3)) & 7) << 4);
  a.la = buf + ((lane >> 3) & 1) * 1024 + (lane >> 4) * 128 + (((lane ^ (lane >> 4)) & 7) << 4);
  a.sb = a.sa ^ 64; a.lc = a.lb ^ 64;
  asm volatile("" : "+r"(a.sa), "+r"(a.sb), "+r"(a.lb), "+r"(a.lc), "+r"(a.la));
  return a;
}
__device__ __forceinline__ void kgen_unit(const KgenRaw& r, const KgenAddr& ad, uint32_t zero, float (&k)[5][4], float& k2048, float& sc) {
  const float dt = bf_round(expf(bf_lo(r.ldt)));
  const float a2 = bf_round(ex2(bf_lo(r.la) * 1.4426950408889634f)) * (dt * -1.4426950408889634f);
  const float f = bf_lo(r.ai) * dt;
  const float r128 = f * 20.371832715762604f;
  const uint32_t ex = min(max(__reduce_max_sync(0xffffffffu, max(r.cr & 0x7fffu, r.ci & 0x7fffu)) >> 7, 1u), 253u);
  const float cs = uf((254u - ex) << 23);
  sc = 2.f * dt * uf(ex << 23);
  const cpx C = {bf_lo(r.cr) * cs, -bf_lo(r.ci) * cs};
  auto put = [&](const __half2 (&v)[8], uint32_t off) {
    stsm4(ad.sa + off, hu(v[0]), hu(v[1]), hu(v[2]), hu(v[3]));
    stsm4(ad.sb + off, hu(v[4]), hu(v[5]), hu(v[6]), hu(v[7]));
  };
  uint32_t A[4][4], B[5][2][4];
  auto get = [&](int j, uint32_t off) {
    __syncwarp();
    ldsm4(B[j][0], ad.lb + off);
    ldsm4(B[j][1], ad.lc + 512 + off);
  };
  auto tile = [&](int j) {
    k[j][0] = k[j][1] = k[j][2] = k[j][3] = 0.f;
#pragma unroll
    for (int s = 0; s < 4; s++) mma_h(k[j], A[s], B[j][s >> 1][2 * (s & 1)], B[j][s >> 1][2 * (s & 1) + 1]);
  };
  auto after = [&](cpx v, uint32_t dep) { return cpx{uf(fu(v.r) ^ (dep & zero)), v.i}; };
  const cpx w1 = polar(a2, f), w128 = polar(a2 * 128.f, (r128 - rintf(r128)) * 6.283185307179586f);
  const cpx w2 = csq(w1), w4 = csq(w2);
  __half2 t0[8], t1[8], t2[8], t3[8], t4[8];
  const hmul m2 = mk_mul(w2), m4 = mk_mul(w4), m128 = mk_mul(w128);
  t0[0] = __floats2half2_rn(1.f, 0.f); t0[1] = __floats2half2_rn(w1.r, w1.i); t0[2] = m2.a; t0[4] = m4.a;
  t0[3] = hcm(t0[1], m2); t0[5] = hcm(t0[1], m4); t0[6] = hcm(t0[2], m4); t0[7] = hcm(t0[3], m4);
  put(t0, 0); get(0, 0);
  t1[0] = m128.a;
#pragma unroll
  for (int i = 1; i < 8; i++) t1[i] = hcm(t0[i], m128);
  put(t1, 1024); get(1, 1024);
  {
    cpx w8 = csq(after(w4, B[0][0][0]));
    w8.i = -w8.i;
    const cpx w16 = csq(w8), w32 = csq(w16), w64 = csq(w32);
    const hmul m8 = mk_mul(w8), m16 = mk_mul(w16), m32 = mk_mul(w32), m64 = mk_mul(w64);
    __half2 a[8];
    a[0] = __floats2half2_rn(C.r, C.i); a[1] = hcm(a[0], m8);
    a[2] = hcm(a[0], m16); a[3] = hcm(a[1], m16);
#pragma unroll
    for (int i = 0; i < 4; i++) a[4 + i] = hcm(a[i], m32);
    put(a, 0);
#pragma unroll
    for (int i = 0; i < 8; i++) a[i] = hcm(a[i], m64);
    put(a, 1024);
    __syncwarp();
#pragma unroll
    for (int s = 0; s < 4; s++) ldsm4(A[s], (ad.la ^ (s << 5)) + s * 256);
  }
  const cpx w256 = csq(after(w128, B[1][0][0]));
  const hmul m256 = mk_mul(w256);
  t2[0] = m256.a;
#pragma unroll
  for (int i = 1; i < 8; i++) t2[i] = hcm((i & 1) ? t1[i & 6] : t0[i & 6], m256);
  put(t2, 0); get(2, 0);
  tile(0); tile(1);
  const cpx w512 = csq(after(w256, A[0][0]));
  const hmul m512 = mk_mul(w512);
  t3[0] = m512.a;
#pragma unroll
  for (int i = 1; i < 8; i++) t3[i] = hcm((i & 2) ? t2[i & 5] : ((i & 1) ? t1[i & 4] : t0[i & 4]), m512);
  put(t3, 1024); get(3, 1024);
  tile(2);
  const cpx w1024 = csq(after(w512, B[2][0][0])), we = csq(w1024);
  const hmul m1024 = mk_mul(w1024);
  t4[0] = m1024.a;
#pragma unroll
  for (int i = 1; i < 8; i++) t4[i] = hcm((i & 4) ? t3[i & 3] : ((i & 2) ? t2[i & 1] : t1[0]), m1024);
  put(t4, 0); get(4, 0);
  tile(3); tile(4);
  k2048 = (C.r * we.r + C.i * we.i) * sc;
}

__device__ __forceinline__ void build_tables(uint32_t tb, int lane, float (&k)[5][4], float k2048) {
  const int g = lane >> 2, c = lane & 3;
  const uint32_t kc = tb + T_KC + 16;
  {
    const uint32_t a0 = kc + 16 * g + 4 * c, a2 = kc + 2 * (256 + 4 * g + c);
    const uint32_t a3 = kc + 2 * (384 + 2 * g + 64 * (c & 1) + (c >> 1)), a4 = kc + 2 * (512 + g + 32 * c);
#pragma unroll
    for (int r = 0; r < 2; r++) {
      sts32(a0 + 128 * r, pack_bf(k[0][2 * r], k[0][2 * r + 1]));
      sts32(a0 + 128 * r + 256, pack_bf(k[1][2 * r], k[1][2 * r + 1]));
      const uint32_t w2 = pack_bf(k[2][2 * r], k[2][2 * r + 1]);
      const uint32_t w3 = pack_bf(k[3][2 * r], k[3][2 * r + 1]);
      const uint32_t w4 = pack_bf(k[4][2 * r], k[4][2 * r + 1]);
      sts16(a2 + 64 * r, w2); sts16(a2 + 64 * r + 128, w2 >> 16);
      sts16(a3 + 32 * r, w3); sts16(a3 + 32 * r + 64, w3 >> 16);
      sts16(a4 + 16 * r, w4); sts16(a4 + 16 * r + 32, w4 >> 16);
    }
  }
  if (lane == 0) { sts16(kc + 2 * 640, pack_bf(k2048, 0.f)); sts32(kc - 4, 0); }
  __syncwarp();
  const uint32_t td = tb + T_D + 32;
#pragma unroll
  for (int hf = 0; hf < 2; hf++) {
    const uint2 v = lds64(kc + 256 * hf + 8 * lane);
    const uint32_t pv = lds32(kc + 256 * hf + 8 * lane - 4);
    sts128(td + 512 * hf + 16 * lane, __byte_perm(v.x, pv, 0x7610), __byte_perm(v.x, v.x, 0x1032), __byte_perm(v.y, v.x, 0x7610),
           __byte_perm(v.y, v.y, 0x1032));
  }
#pragma unroll
  for (int hf = 0; hf < 2; hf++) {
    const uint32_t v = lds32(kc + 512 + 128 * hf + 4 * lane), nx = lds32(kc + 516 + 128 * hf + 4 * lane);
    uint32_t w0 = __byte_perm(v, v, 0x1010);
    const uint32_t w1 = w0;
    if (hf == 0) { const uint32_t pv = lds32(kc + 508); if (lane == 0) w0 = __byte_perm(v, pv, 0x7610); }
    sts128(td + 1024 + 512 * hf + 16 * lane, w0, w1, __byte_perm(v, v, 0x1032), __byte_perm(nx, v, 0x7610));
  }
  {
    const uint32_t kk = lds16(kc + 2 * 384);
    const uint32_t w = lane < 3 ? (kk | (kk << 16)) : (lane == 3 ? (kk << 16) : 0u);
    if (lane < 24) sts32(td + 4 * (lane < 16 ? 512 + lane : lane - 24), w);
    const uint32_t lo_ = lds16(kc + 2 * 511), le_ = lds16(kc + 2 * 512);
    const uint32_t ja = tb + T_5 + (lane < 16 ? 4 * lane : 256 + 4 * lane);
    sts32(ja, lane == 16 ? (le_ << 16) : 0u);
    sts32(ja + 384, lane == 16 ? (lo_ << 16) : 0u);
    sts32(tb + (lane < 16 ? T_7 : T_9 - 64) + 4 * lane, 0u);
  }
#pragma unroll
  for (int s = 0; s < 2; s++) {
    const uint32_t b = kc + 2 * (s ? 512 : 384) + 8 * lane;
    const uint2 v = lds64(b);
    uint32_t em = lds16(b - 2), e0 = v.x;
    const uint32_t e4 = lds16(b + 8);
    if (lane == 0) { em = 0; e0 = 0; }
    sts64(tb + (s ? T_7 : T_3) + 64 + 8 * lane, __byte_perm(v.x, em, 0x5432), __byte_perm(v.y, v.x, 0x7632));
    sts64(tb + (s ? T_9 : T_5) + 64 + 8 * lane, __byte_perm(v.y, e0, 0x5410), __byte_perm(e4, v.y, 0x5410));
  }
  __syncwarp();
}

__device__ __forceinline__ uint32_t box2w(int lo, int n, int o) {
  return ((unsigned)(o - lo) < (unsigned)n ? 0x3F80u : 0u) | ((unsigned)(o + 1 - lo) < (unsigned)n ? 0x3F800000u : 0u);
}

__device__ __forceinline__ void conv_channel(uint32_t ub, uint32_t tb, int lane, uint4* ydst) {
  const int g = lane >> 2, c = lane & 3, x = g - 2 * c;
  const int mi = lane >> 3;
  const uint32_t qa = ub + U_PAD + 16 * (lane & 7) + ((mi == 0 || mi == 3) ? U_ODD : 0) - (mi == 0 ? 16 : 0);
  const uint32_t hb = ub + U_PAD + (mi & 1) * U_ODD + 16 * ((lane >> 4) + (lane & 7)) - 16;
  const uint32_t kv = lds16(tb + T_KC + 16 + 2 * 512);
  const int oh = c < 2 ? 8 + 2 * c : 2 * c - 8, og = c < 3 ? 2 * c : -10;
  uint32_t bx[4] = {box2w(g - 4, 9, 2 * c), box2w(g - 3, 7, 2 * c), box2w(g - 4, 9, oh), box2w(g - 3, 7, oh)};
  uint32_t by[4] = {box2w(g - 10, 5, 2 * c - 8), box2w(g - 5, 3, 2 * c - 8), box2w(g - 10, 5, og), box2w(g - 5, 3, og)};
  uint32_t lb0 = ((unsigned)(x + 5) < 2u ? kv : 0u) | ((unsigned)(x + 4) < 2u ? kv << 16 : 0u);
  uint32_t lb1 = ((unsigned)(x - 3) < 2u ? kv : 0u) | ((unsigned)(x - 4) < 2u ? kv << 16 : 0u);
  const int q0 = g - 1, q1 = c < 3 ? g : g - 2;
  uint32_t y0a = ub + U_PAD + (q0 & 1) * U_ODD + 16 * (q0 >> 1) + 4 * c;
  uint32_t y1a = ub + U_PAD + (q1 & 1) * U_ODD + 16 * (q1 >> 1) + 4 * c;
#pragma unroll
  for (int i = 0; i < 4; i++) asm volatile("" : "+r"(bx[i]), "+r"(by[i]));
  asm volatile("" : "+r"(lb0), "+r"(lb1), "+r"(y0a), "+r"(y1a));
  mbar_wait(BAR(MB_UFULL));
  mbar_wait(BAR(MB_EMPTY + 15));
  TS(36);
  float acc[16][4];
  {
    uint32_t z09[8], z07[8], zm9[8], zm7[8];
#pragma unroll
    for (int i = 0; i < 8; i++) {
      uint32_t h[4];
      ldsm4(h, hb + 128 * i);
      float y0, y1, y2, y3, w0, w1, w2, w3;
      mma0(y0, y1, y2, y3, bx[0], bx[1], bx[2], bx[3], h[2], c < 2 ? h[3] : h[1]);
      mma0(w0, w1, w2, w3, bx[0], bx[1], bx[2], bx[3], h[1], c < 2 ? h[2] : h[0]);
      z09[i] = pack_bf(y0, y1); z07[i] = pack_bf(y2, y3);
      zm9[i] = pack_bf(w0, w1); zm7[i] = pack_bf(w2, w3);
    }
  uint32_t f3[3][4][4];
  {
    const uint32_t fa = tb + T_7 + 4 * (16 + x);
#pragma unroll
    for (int tt = 0; tt < 3; tt++)
#pragma unroll
      for (int D = 0; D < 4; D++) {
        const uint32_t a = fa + (tt == 0 ? 316 : (tt == 1 ? 320 : 0)) + 64 * D;
        f3[tt][D][0] = lds32(a); f3[tt][D][1] = lds32(a + 32); f3[tt][D][2] = lds32(a - 32); f3[tt][D][3] = lds32(a);
      }
  }
    float a[4][2][4];
#pragma unroll
    for (int kap = 0; kap < 4; kap++)
#pragma unroll
      for (int sg = 0; sg < 2; sg++)
#pragma unroll
        for (int bk = 3; bk >= kap; bk--) {
          const uint32_t(&q0_)[4] = f3[sg ? 2 : 0][bk - kap];
          const uint32_t(&q1_)[4] = f3[sg ? 2 : 1][bk - kap];
          float(&a0)[4] = a[bk][0];
          float(&a1)[4] = a[bk][1];
          if (sg == 0 && kap == 0) {
            mma0(a0[0], a0[1], a0[2], a0[3], q0_[0], q0_[1], q0_[2], q0_[3], z09[0], z09[1]);
            mma0(a1[0], a1[1], a1[2], a1[3], q1_[0], q1_[1], q1_[2], q1_[3], zm9[0], zm9[1]);
          } else {
            mma(a0[0], a0[1], a0[2], a0[3], q0_[0], q0_[1], q0_[2], q0_[3], sg ? zm7[2 * kap] : z09[2 * kap], sg ? zm7[2 * kap + 1] : z09[2 * kap + 1]);
            mma(a1[0], a1[1], a1[2], a1[3], q1_[0], q1_[1], q1_[2], q1_[3], sg ? z07[2 * kap] : zm9[2 * kap], sg ? z07[2 * kap + 1] : zm9[2 * kap + 1]);
          }
        }
    SPLIT();
#pragma unroll
    for (int i = 0; i < 8; i++) {
      uint32_t h[4];
      ldsm4(h, qa + 128 * i);
      const float ci[4] = {a[i >> 1][0][2 * (i & 1)], a[i >> 1][0][2 * (i & 1) + 1], a[i >> 1][1][2 * (i & 1)], a[i >> 1][1][2 * (i & 1) + 1]};
      mmac(acc[8 + i], h[0], h[1], h[2], h[3], lb0, lb1, ci);
    }
  }
  TS(44);
  {
    uint2 a5[10], a3[10];
    const uint32_t aa = tb + T_5 + 4 * (8 + 2 * g - 2 * c);
#pragma unroll
    for (int m = 0; m < 10; m++) { a5[m] = lds64(aa + 32 * m); a3[m] = lds64(aa + 384 + 32 * m); }
    uint32_t x5[12][2], x3[12][2];
    auto ygen = [&](int kap) {
#pragma unroll
      for (int hh = 0; hh < 2; hh++) {
        float y0, y1, y2, y3;
        mma0(y0, y1, y2, y3, by[0], by[1], by[2], by[3], lds32(y0a + 128 * kap + 64 * hh), lds32(y1a + 128 * kap + 64 * hh));
        x5[kap][hh] = pack_bf(y0, y1);
        x3[kap][hh] = pack_bf(y2, y3);
      }
    };
    ygen(11); ygen(10); ygen(9); ygen(8);
#pragma unroll
    for (int kap = 11; kap >= 0; kap--) {
      if (kap >= 4) ygen(kap - 4);
#pragma unroll
      for (int sg = 0; sg < 2; sg++)
#pragma unroll
        for (int i = 4; i >= 0; i--) {
          const int be = kap + 4 + i;
          if (be <= 15) {
            const uint2 &hi = sg ? a3[2 * i + 1] : a5[2 * i + 1], &lo = sg ? a3[2 * i] : a5[2 * i];
            const uint32_t b0 = sg ? x3[kap][0] : x5[kap][0], b1 = sg ? x3[kap][1] : x5[kap][1];
            if (be < 8 && i == 0 && sg == 0) mma0(acc[be][0], acc[be][1], acc[be][2], acc[be][3], hi.x, hi.y, lo.x, lo.y, b0, b1);
            else mma(acc[be][0], acc[be][1], acc[be][2], acc[be][3], hi.x, hi.y, lo.x, lo.y, b0, b1);
          }
        }
    }
  }
  TS(45);
  {
    const uint32_t st = tb + T_ST + lane * 8;
#pragma unroll
    for (int be = 4; be < 12; be++) sts64(st + 256 * be, pack_bf(acc[be][0], acc[be][1]), pack_bf(acc[be][2], acc[be][3]));
    SPLIT();
    uint32_t F[66], qd[8][4];
    const uint32_t fa = tb + T_D + 32 + 4 * x;
#pragma unroll
    for (int i = 0; i < 32; i++) {
      const int s = 120 - (i >> 2) - 8 * (i & 3);
      uint32_t(&q)[4] = qd[i & 7];
      ldsm4(q, qa + 16 * s);
      const int m = 16 * (i & 3) + 2 * (i >> 2);
      F[m] = lds32(fa + 32 * m); F[m + 1] = lds32(fa + 32 * m + 32);
#pragma unroll
      for (int be = 15; be >= 12; be--) {
        const int de = 8 * be - s;
        float(&a)[4] = (be >= 14 && !(i & 1)) ? acc[be - 4] : acc[be];
        if (de >= 0 && be >= 14 && i == 2 * (15 - be)) mma0(a[0], a[1], a[2], a[3], q[0], q[1], q[2], q[3], F[2 * de + 1], F[2 * de]);
        else if (de >= 0) mma(a[0], a[1], a[2], a[3], q[0], q[1], q[2], q[3], F[2 * de + 1], F[2 * de]);
      }
    }
#pragma unroll
    for (int i = 0; i < 8; i++) acc[14 + (i >> 2)][i & 3] += acc[10 + (i >> 2)][i & 3];
    F[64] = lds32(fa + 32 * 64); F[65] = lds32(fa + 32 * 65);
    uint32_t qp = qa + 128 * 11, sta = st + 256 * 10;
    uint4* yd = ydst + 7 * 32;
#pragma unroll
    for (int i = 0; i < 6; i++) ldsm4(qd[i], qp - 16 * i);
    uint2 sv = lds64(sta + 256);
    float ci[4] = {bf_lo(sv.x), bf_hi(sv.x), bf_lo(sv.y), bf_hi(sv.y)};
    float T[5][4];
#pragma unroll
    for (int i = 0; i < 16; i++) T[i >> 2][i & 3] = acc[12 + (i >> 2)][i & 3];
    nb_sync(NB_YZ, 160);
    TS(46);
#pragma unroll 1
    for (int bp = 5; bp >= 0; bp--) {
      uint32_t held[2];
#pragma unroll
      for (int o = 1; o >= 0; o--) {
#pragma unroll
        for (int k = 4; k >= 1; k--) mmac(T[k], qd[0][0], qd[0][1], qd[0][2], qd[0][3], F[16 * k + 1], F[16 * k], T[k - 1]);
        mmac(T[0], qd[0][0], qd[0][1], qd[0][2], qd[0][3], F[1], F[0], ci);
        ldsm4(qd[6], qp - 16 * 6);
        ldsm4(qd[7], qp - 16 * 7);
        sv = lds64(sta);
#pragma unroll
        for (int i = 1; i < 8; i++) {
#pragma unroll
          for (int k = 3; k >= 0; k--)
            mma(T[k][0], T[k][1], T[k][2], T[k][3], qd[i][0], qd[i][1], qd[i][2], qd[i][3], F[16 * k + 2 * i + 1], F[16 * k + 2 * i]);
          if (i < 7) ldsm4(qd[i - 1], qp - 128 - 16 * (i - 1));
          if (i == 2) {
            const uint32_t w0 = pack_bf(T[4][0], T[4][1]), w1 = pack_bf(T[4][2], T[4][3]);
            if (o) { held[0] = w0; held[1] = w1; }
            else st_x(yd, nz(w0), w1, held[0], held[1]);
          }
          if (i == 4) {
            if (2 * bp + o <= 4) sv = make_uint2(0, 0);
            ci[0] = bf_lo(sv.x); ci[1] = bf_hi(sv.x); ci[2] = bf_lo(sv.y); ci[3] = bf_hi(sv.y);
          }
        }
        qp -= 128; sta -= 256;
      }
      yd -= 32;
    }
#pragma unroll
    for (int B = 1; B >= 0; B--)
      st_x(ydst + B * 32, nz(pack_bf(T[2 * B][0], T[2 * B][1])), pack_bf(T[2 * B][2], T[2 * B][3]),
           pack_bf(T[2 * B + 1][0], T[2 * B + 1][1]), pack_bf(T[2 * B + 1][2], T[2 * B + 1][3]));
  }
}

__device__ __forceinline__ void dual_exp(const uint32_t* w, uint32_t* e) {
  const float L = 1.44268798828125f;
  uint32_t mx = bmax2(bmax2(w[0], w[1]), bmax2(w[2], w[3]));
  uint32_t mn = bmin2(bmin2(w[0], w[1]), bmin2(w[2], w[3]));
  mx = bmax2(mx, __shfl_xor_sync(0xffffffffu, mx, 1));
  mn = bmin2(mn, __shfl_xor_sync(0xffffffffu, mn, 1));
  mx = bmax2(mx, __shfl_xor_sync(0xffffffffu, mx, 2));
  mn = bmin2(mn, __shfl_xor_sync(0xffffffffu, mn, 2));
  const float mx0 = bf_lo(mx) * -L, mx1 = bf_hi(mx) * -L, mn0 = bf_lo(mn) * L, mn1 = bf_hi(mn) * L;
#pragma unroll
  for (int i = 0; i < 2; i++) {
    const float a0 = bf_lo(w[2 * i]), a1 = bf_hi(w[2 * i]), b0 = bf_lo(w[2 * i + 1]), b1 = bf_hi(w[2 * i + 1]);
    e[2 * i] = pack_bf(ex2(fmaf(a0, L, mx0)), ex2(fmaf(b0, L, mx0)));
    e[2 * i + 1] = pack_bf(ex2(fmaf(a1, L, mx1)), ex2(fmaf(b1, L, mx1)));
    e[4 + 2 * i] = pack_bf(ex2(fmaf(a0, -L, mn0)), ex2(fmaf(b0, -L, mn0)));
    e[5 + 2 * i] = pack_bf(ex2(fmaf(a1, -L, mn1)), ex2(fmaf(b1, -L, mn1)));
  }
}
__device__ __forceinline__ void normalise(uint32_t* e, const float (&s)[4]) {
  const uint32_t r = pack_bf(rcp(s[0]), rcp(s[2]));
  const __nv_bfloat162 rr = *(const __nv_bfloat162*)&r;
#pragma unroll
  for (int i = 0; i < 4; i++) {
    const __nv_bfloat162 v = __hmul2(*(const __nv_bfloat162*)&e[i], (i & 1) ? __high2bfloat162(rr) : __low2bfloat162(rr));
    e[i] = *(const uint32_t*)&v;
  }
}
__host__ __device__ constexpr uint64_t qdesc(uint32_t addr) { return mkdesc(addr, 128, 256, 0); }

__global__ void __launch_bounds__(NTHREADS, 1)
fused_kernel(const Params P, const __grid_constant__ CUtensorMap mx, const __grid_constant__ CUtensorMap mw,
             const __grid_constant__ CUtensorMap mo, const __grid_constant__ CUtensorMap mu,
             const __grid_constant__ CUtensorMap mout, const __grid_constant__ CUtensorMap mw4) {
  constexpr uint32_t sb = SB;
  const int tid = threadIdx.x, lane = tid & 31;
  const int warp = __shfl_sync(0xffffffffu, tid >> 5, 0);
  const int b = blockIdx.x, oct = b >> 3, i8 = b & 7;
  const int rt = (((oct & 4) ? ~oct : oct) & 3) * 2 + (i8 >> 2);
  const int hp = (oct >> 2) * 4 + (i8 & 3);

  const int wg = warp >> 2, w = warp & 3;
  const int d = b * 4 + ((tid >> 5) & 3);
  const KgenRaw raw = kgen_load(P, d, tid >> 7, lane);
  const unsigned short dsk = __ldg((const unsigned short*)P.Dskip + d);
  if (tid < 384) {
    asm volatile("prefetch.tensormap [%0];" ::"l"(&mu) : "memory");
    asm volatile("prefetch.tensormap [%0];" ::"l"(&mw) : "memory");
    asm volatile("prefetch.tensormap [%0];" ::"l"(&mx) : "memory");
    asm volatile("prefetch.tensormap [%0];" ::"l"(&mw4) : "memory");
  }
  if (warp == 12) {
    if (lane == 0) {
#pragma unroll
      for (int i = 0; i < 9; i++) mbar_init(BAR(i), 1);
      asm volatile("fence.mbarrier_init.release.cluster;" ::: "memory");
    }
    __syncwarp();
    if (lane < 9) mbar_expect(BAR(0) + 8 * lane, (lane == 5 || lane == 7) ? 40960 : ((lane == 0 || lane > 5) ? 16384 : 28672));
    __syncwarp();
    e_tma3d(sb + OFF_W, &mw, BAR(MB_FULL), hp * 32, 0, 0);
    e_tma2d(sb + OFF_X + 3 * 16384, &mx, BAR(MB_FULL), 0, rt * 256);
    nb_arrive(NB_PROD, 192);
  } else if (warp == 13) {
    if (lane == 0) {
#pragma unroll
      for (int i = 9; i < 39; i++) mbar_init(BAR(i), i < MB_EMPTY ? 1 : (i < MB_AUX ? 4 : 8));
      asm volatile("fence.mbarrier_init.release.cluster;" ::: "memory");
    }
    __syncwarp();
    if (lane < 9) mbar_expect(BAR(MB_FULL + 8) + 8 * lane, lane < 8 ? 16384 : 131072);
    nb_arrive(NB_PROD, 192);
  }
  const uint32_t tb = sb + OFF_T + w * T_CH;
  const uint32_t kp = wg >= 2 ? sb + OFF_STG0 + 16384 + w * 2048 : ((tb + 127) & ~127u) + wg * 2048;
  const KgenAddr kad = kgen_addr(lane, wg == 3 ? sb + OFF_X + 32768 + w * 2048 : kp);
  if (wg == 1) nb_sync(NB_PROD, 192);
  if (warp == 12) {
#pragma unroll 1
    for (int kb = 1; kb < 4; kb++) {
      if (kb == U_AT) e_tma4d(sb + OFF_STG0, &mu, BAR(MB_URAW), i8 * 64, oct * 2);
      e_tma3d(sb + OFF_W + kb * 12288, &mw, BAR(MB_FULL) + 8 * kb, hp * 32, kb * 64, 0);
      e_tma2d(sb + OFF_X + (kb < 2 ? kb + 3 : kb - 2) * 16384, &mx, BAR(MB_FULL) + 8 * kb, kb * 64, rt * 256);
    }
    e_prefetch(P.x + (size_t)(rt * 256 + hp * 8) * 512, 8192);
    e_tma4d(sb + OFF_W + 4 * 12288, &mw4, BAR(MB_FULL + 4), hp * 32, 4);
    e_tma4d(sb + OFF_W + 6 * 12288, &mw4, BAR(MB_FULL + 6), hp * 32, 6);
    if (smem_u32(smem_raw) != SB) __trap();
    if (lane == 0) TS1(54);
  }
  float k[5][4], k2048, ksc;
  kgen_unit(raw, kad, blockIdx.y, k, k2048, ksc);
  TS(40 + wg);
  if ((fu(k[0][0]) & fu(k[1][0]) & fu(k[2][0]) & fu(k[3][0]) & fu(k[4][0])) == 0xffffffffu) sts32(kp, 0);
  if (wg == 3) {
    nb_sync(0, 512);
    if (warp == 12) {
      asm volatile("fence.proxy.async.shared::cta;" ::: "memory");
      e_tma2d(sb + OFF_X + 2 * 16384, &mx, BAR(MB_FULL + 4), 256, rt * 256);
      if (X2_AT < 0) e_prefetch(P.x + (size_t)(rt * 256 + 128 + hp * 8) * 512, 8192);
    }
  } else if (wg) {
    nb_arrive(0, 512);
  }
  k2048 += __shfl_xor_sync(0xffffffffu, k2048, 16);
  k2048 += __shfl_xor_sync(0xffffffffu, k2048, 8);
  if (wg != 2) {
    uint32_t h[10];
#pragma unroll
    for (int j = 0; j < 10; j++) h[j] = hu(__floats2half2_rn(k[j >> 1][2 * (j & 1)], k[j >> 1][2 * (j & 1) + 1]));
    sts128(kp + lane * 16, h[0], h[1], h[2], h[3]);
    sts128(kp + 512 + lane * 16, h[4], h[5], h[6], h[7]);
    sts128(kp + 1024 + lane * 16, h[8], h[9], fu(k2048), fu(ksc));
  }
  if (wg == 0) { nb_arrive(NB_PREP, 512); nb_sync(0, 512); }
  else if (wg != 2) nb_arrive(NB_PREP, 512);
  else nb_sync(NB_PREP, 512);
  if (warp >= 12) {
    asm volatile("setmaxnreg.dec.sync.aligned.u32 32;");
    if (warp == 12) {
      uint32_t slot = sb + OFF_X + 3 * 16384;
#pragma unroll 1
      for (int n = 0; n < 11; n++) {
        mbar_spin(BAR(MB_EMPTY) + 8 * n);
        const int m = n + 5;
        e_tma2d(slot, &mx, BAR(MB_FULL) + 8 * m, (m & 7) * 64, rt * 256 + (m >> 3) * 128);
        slot = slot == sb + OFF_X + 4 * 16384 ? sb + OFF_X : slot + 16384;
        if (n == X2_AT) e_prefetch(P.x + (size_t)(rt * 256 + 128 + hp * 8) * 512, 8192);
        if (n == 7) {
          e_prefetch(P.wo + (size_t)b * 2048, 4096);
          asm volatile("prefetch.tensormap [%0];" ::"l"(&mo) : "memory");
          asm volatile("prefetch.tensormap [%0];" ::"l"(&mout) : "memory");
        }
      }
#pragma unroll 1
      for (int i = 0; i < 8; i++) {
        mbar_wait(BAR(MB_EMPTY + 10) + 8 * ((0x54332100u >> (4 * i)) & 7));
        const int w0 = (0x54736210u >> (4 * i)) & 7;
        e_tma3d(sb + OFF_W + w0 * 16384, &mo, BAR(MB_WO), 0, w0 * 64, (hp & 3) * 2);
      }
    } else {
      if (warp == 15) {
        const uint4 v0 = __ldg((const uint4*)P.wphi + hp * 64 + lane), v1 = __ldg((const uint4*)P.wphi + hp * 64 + 32 + lane);
        sts128(sb + OFF_PHI + (lane & 1) * 256 + (lane >> 1) * 16, v0.x, v0.y, v0.z, v0.w);
        sts128(sb + OFF_PHI + 512 + (lane & 1) * 256 + (lane >> 1) * 16, v1.x, v1.y, v1.z, v1.w);
        const uint32_t one = (((lane >> 3) ^ (lane >> 4)) & 1) ? 0u : ((lane & 1) ? 0x3F800000u : 0x3F80u);
        const int q = (lane >> 1) & 3;
        sts128(sb + OFF_EYE + lane * 16, q == 0 ? one : 0u, q == 1 ? one : 0u, q == 2 ? one : 0u, q == 3 ? one : 0u);
        sts64(sb + OFF_ONE + lane * 8, 0x3F803F80u, 0x3F803F80u);
        asm volatile("fence.proxy.async.shared::cta;" ::: "memory");
        nb_arrive(NB_KREAD, 160);
      }
      uint32_t* cnt = (uint32_t*)(P.xs + X_CNT) + (warp == 13 ? i8 : (warp == 14 ? 8 + rt : 16 + oct)) * 32;
      const unsigned target = (ld_x32(cnt) & ~15u) + 16;
      if (warp != 14) {
        if (warp == 15) mbar_wait(BAR(MB_EMPTY + ZERO_STEP));
        uint4* pz = P.xs + (warp == 13 ? X_PART + (hp * 8 + rt) * 144 : X_Y + b * 1024) + lane;
#pragma unroll 1
        for (int i = (warp == 13 ? 144 : 1024) - lane; i > 0; i -= 32, pz += 32) st_x(pz, 0, 0, 0, 0);
      }
      if (warp == 15) __syncwarp();
      else nb_sync(warp == 13 ? NB_INIT : NB_ODONE, warp == 13 ? 160 : 288);
      if (lane == 0) asm volatile("red.release.gpu.global.add.u32 [%0], %1;" ::"l"(cnt), "r"(warp == 15 ? 2 : 1) : "memory");
      if (lane == 0) TS1(warp == 13 ? 50 : (warp == 14 ? 57 : 53));
      asm volatile("fence.proxy.async.shared::cta;" ::: "memory");
      if (warp == 13) cnt += ((lane & 1 ? b >> 4 : i8 ^ (lane & 4)) - i8) * 32;
#pragma unroll 1
      for (int i = 0; i < SPIN_MAX; i++) {
        unsigned v;
        asm volatile("ld.acquire.gpu.global.u32 %0, [%1];" : "=r"(v) : "l"(cnt) : "memory");
        if (__all_sync(0xffffffffu, (int)(v - target) >= 0)) break;
      }
      if (lane == 0) TS1(warp == 13 ? 51 : (warp == 14 ? 58 : 55));
      if (warp == 15) { nb_arrive(NB_YZ, 160); return; }
      asm volatile("fence.proxy.async.global;" ::: "memory");
      if (warp == 13) {
        mbar_wait(BAR(MB_EMPTY + 11));
        e_expect(BAR(MB_UFULL), 4 * U_CH);
        e_bulk(sb + OFF_U, P.xs + X_UT + b * (U_CH / 4), 4 * U_CH, BAR(MB_UFULL));
      } else {
        const uint4* src = P.xs + X_O + (rt * 4 + (hp >> 2)) * 4096;
        e_expect(BAR(MB_OA), 14336);
        e_bulk(sb + OFF_STG0, src + 3200, 14336, BAR(MB_OA));
        e_expect(BAR(MB_OC), 32768);
        e_bulk(sb + OFF_X + 32768, src, 32768, BAR(MB_OC));
        nb_sync(NB_BDONE, 288);
        asm volatile("fence.proxy.async.shared::cta;" ::: "memory");
        e_expect(BAR(MB_OB), 18432);
        e_bulk(sb + OFF_U, src + 2048, 18432, BAR(MB_OB));
      }
    }
    return;
  }

  const int t = tid & 127;
  const int g = lane >> 2, c = lane & 3;
  {
    if (wg == 2) {
      asm volatile("setmaxnreg.inc.sync.aligned.u32 160;");
#pragma unroll
      for (int j = 0; j < 5; j++) { k[j][0] *= ksc; k[j][1] *= ksc; k[j][2] *= ksc; k[j][3] *= ksc; }
#pragma unroll 1
      for (int q = 0; q < 3; q++) {
        const uint32_t src = (q == 2 ? kp : ((tb + 127) & ~127u) + q * 2048) + lane * 16;
        const uint4 v0 = lds128(src), v1 = lds128(src + 512), v2 = lds128(src + 1024);
        const uint32_t h[10] = {v0.x, v0.y, v0.z, v0.w, v1.x, v1.y, v1.z, v1.w, v2.x, v2.y};
#pragma unroll
        for (int j = 0; j < 10; j++) {
          const float2 f = __half22float2(*(const __half2*)&h[j]);
          k[j >> 1][2 * (j & 1)] = fmaf(f.x, uf(v2.w), k[j >> 1][2 * (j & 1)]);
          k[j >> 1][2 * (j & 1) + 1] = fmaf(f.y, uf(v2.w), k[j >> 1][2 * (j & 1) + 1]);
        }
        k2048 += uf(v2.z);
      }
#pragma unroll
      for (int o2 = 4; o2; o2 >>= 1) k2048 += __shfl_xor_sync(0xffffffffu, k2048, o2);
      if (lane == 0) k[0][0] += bf_lo(dsk);
      __syncwarp();
      if (lane == 0) mbar_arrive(BAR(MB_AUX));
      TS(34);
      build_tables(tb, lane, k, k2048);
      TS(35);
      uint4* const g_y = P.xs + X_Y;
      conv_channel(sb + OFF_U + w * U_CH, tb, lane, g_y + (size_t)d * 256 + lane);
      nb_arrive(NB_BDONE, 288);
      TS(37);
      const int lam = w * 8 + g;
      const uint4* src = g_y + (size_t)(oct * 32 + c * 8) * 256 + i8 * 32 + lam;
      uint4 v[8];
#pragma unroll 1
      for (int it = 0; it < SPIN_MAX; it++) {
        uint32_t m = 0xffffffffu;
#pragma unroll
        for (int i = 0; i < 8; i++) v[i] = ld_x(src + i * 256);
#pragma unroll
        for (int i = 0; i < 8; i++) m = min(m, v[i].x);
        if (__all_sync(0xffffffffu, m != 0)) break;
      }
      __nv_bfloat16* dst = P.out + (size_t)(i8 * 256 + (lam >> 2) * 16 + (lam & 3) * 2) * 1024 + 512 + oct * 32 + c * 8;
#pragma unroll
      for (int i = 0; i < 8; i++) *(uint4*)(dst + (size_t)((i >> 2) * 128 + ((i >> 1) & 1) * 8 + (i & 1)) * 1024) = tr_row(v, i);
      TS(38);
      GT(63);
      if (w == 0) TSDUMP(32);
      return;
    }
    if (wg == 1) {
      mbar_wait(BAR(MB_URAW));
      TS(48);
      uint4* dst = P.xs + X_UT + (i8 * 64 + g) * (U_CH / 16) + (w & 1) * (U_ODD / 16) + U_PAD / 16 + oct * 8 + (w >> 1) * 4 + c;
      const int ln = ((lane >> 1) & 3) + 4 * (lane & 1);
      uint32_t r[8][4];
#pragma unroll
      for (int i = 0; i < 8; i++) ldsm4t(r[i], sb + OFF_STG0 + w * 4096 + ((lane >> 3) * 8 + ln) * 128 + ((i ^ ln) << 4));
#pragma unroll
      for (int i = 0; i < 8; i++) dst[i * (U_CH / 2)] = make_uint4(r[i][0], r[i][1], r[i][2], r[i][3]);
      nb_arrive(NB_INIT, 160);
      if (lane == 0) mbar_arrive(BAR(MB_AUX));
      mbar_wait(BAR(MB_EMPTY + 4));
      mbar_spin(BAR(MB_EMPTY + 6));
    }
    TS(wg * 16 + 1);
  }

  float acc[2][48];
  {
    uint32_t fb = BAR(MB_FULL) + 64 * wg;
    uint32_t da = (uint32_t)mkdesc(sb + OFF_X, 16, 0, 0) + (wg ? 1024 : 3072), db = (uint32_t)mkdesc(sb + OFF_W, 4096, 0, 0);
    constexpr uint64_t ha = mkdesc(0, 0, 1024, 1), hb = mkdesc(0, 0, 512, 2);
    mbar_spin(fb);
    TS(wg * 16 + 2);
#pragma unroll 1
    for (int kb = 0; kb < 8; kb++) {
      WG_FENCE();
#pragma unroll
      for (int k = 0; k < 4; k++) {
        wgmma_ss_n96(acc[0], ha | (da + 2 * k), hb | (db + 64 * k), k ? 1 : kb);
        wgmma_ss_n96(acc[1], ha | (da + 2 * k + 512), hb | (db + 64 * k), k ? 1 : kb);
      }
      WG_COMMIT();
      if (kb < 7) mbar_spin(fb + 8);
      WG_WAIT(1);
      if (kb > 0) e_arrive(fb + 8 * (MB_EMPTY - MB_FULL - 1));
      fb += 8; db += 768;
      da = da == (uint32_t)mkdesc(sb + OFF_X + 65536, 16, 0, 0) ? da - 4096 : da + 1024;
    }
    if (wg == 0) nb_sync(NB_KREAD, 160);
    WG_WAIT(0);
    e_arrive(fb + 8 * (MB_EMPTY - MB_FULL - 1));
    mbar_spin(fb + 8 * (MB_EMPTY - MB_FULL - 1));
  }
  TS(wg * 16 + 3);
  asm volatile("setmaxnreg.inc.sync.aligned.u32 160;");

  constexpr uint32_t stg0 = sb + OFF_STG0, stg1 = sb + OFF_X + 32768;
  uint4* const g_part = P.xs + X_PART;
  uint4* const g_o = P.xs + X_O;
  constexpr uint32_t kvs = stg0;
  auto pack8 = [](const float* a) { return make_uint4(pack_bf(a[0], a[1]), pack_bf(a[2], a[3]), pack_bf(a[4], a[5]), pack_bf(a[6], a[7])); };
  auto feat = [&](const uint4 (&af)[4], float (&p)[4][8]) {
    WG_FENCE();
#pragma unroll
    for (int u = 0; u < 4; u++) wgmma_rs_n16(p[u], af[u], qdesc(sb + OFF_PHI + (u & 1) * 512), 0);
    WG_COMMIT();
  };
  auto packp = [](const float (&p)[4][8], uint32_t (&pw)[16]) {
#pragma unroll
    for (int i = 0; i < 16; i++) pw[i] = pack_bf(p[i >> 2][(i & 1) + 2 * (i & 2)], p[i >> 2][(i & 1) + 2 * (i & 2) + 2]);
  };
  auto contract = [&](float (&kc)[20], uint32_t stg, int acc_in) {
    WG_FENCE();
#pragma unroll
    for (int s = 0; s < 8; s++) wgmma_ss_n40(kc, qdesc(stg + s * SLAB), qdesc(stg + s * SLAB + 2048), s ? 1 : acc_in);
    WG_COMMIT();
    WG_WAIT(0);
  };
  uint32_t eq[32];
  {
    uint4 af[4], aq[4], vp[4];
    float p[4][8];
#pragma unroll
    for (int u = 0; u < 4; u++) af[u] = pack8(acc[u >> 1] + 16 + 8 * (u & 1));
    feat(af, p);
#pragma unroll
    for (int u = 0; u < 4; u++) { aq[u] = pack8(acc[u >> 1] + 8 * (u & 1)); vp[u] = pack8(acc[u >> 1] + 32 + 8 * (u & 1)); }
    WG_WAIT(0);
    uint32_t pw[16], ek[32];
    packp(p, pw);
#pragma unroll
    for (int u = 0; u < 4; u++) dual_exp(pw + 4 * u, ek + 8 * u);
    TS(wg * 16 + 12);
    mbar_wait(BAR(MB_AUX));
    float rs[8][4];
    WG_FENCE();
#pragma unroll
    for (int i = 0; i < 8; i++) wgmma_rs_n8(rs[i], make_uint4(ek[4 * i], ek[4 * i + 1], ek[4 * i + 2], ek[4 * i + 3]), qdesc(sb + OFF_ONE), 0);
    WG_COMMIT();
    feat(aq, p);
    const uint32_t sl = (wg ? stg1 : stg0) + w * SLAB + lane * 16;
#pragma unroll
    for (int i = 0; i < 4; i++) stsm4(sl + (i >> 1) * 4 * SLAB + 2048 + (i & 1) * 512, vp[i].x, vp[i].y, vp[i].z, vp[i].w);
    sts128(sl + (lane >> 4) * (4 * SLAB - 256) + 3072, 0x3F803F80u, 0x3F803F80u, 0x3F803F80u, 0x3F803F80u);
    WG_WAIT(1);
#pragma unroll
    for (int i = 0; i < 8; i++) {
      normalise(ek + 4 * i, rs[i]);
      stsm4(sl + (i >> 2) * 4 * SLAB + (i & 3) * 512, ek[4 * i], ek[4 * i + 1], ek[4 * i + 2], ek[4 * i + 3]);
    }
    asm volatile("fence.proxy.async.shared::cta;" ::: "memory");
    TS(wg * 16 + 13);
    if (wg) {
      nb_arrive(NB_ST0, 256);
    } else {
      float kc[20];
      uint4* pp = g_part + (size_t)(hp * 8 + rt) * 144 + t;
      uint32_t* pz = (uint32_t*)(pp - t + 128) + w * 16 + c * 8 + g;
      asm volatile("" : "+l"(pp), "+l"(pz));
      nb_sync(NB_WG0, 128);
      contract(kc, stg0, 0);
      mbar_wait(BAR(MB_UFULL));
      TS(15);
      nb_sync(NB_ST0, 256);
      contract(kc, stg1, 1);
      TS(6);
      float kv[8];
#pragma unroll
      for (int i = 0; i < 8; i++) kv[i] = w & 2 ? kc[8 + i] : kc[i];
      st_x(pp, nz(pack_bf(kv[0], kv[1])), pack_bf(kv[2], kv[3]), pack_bf(kv[4], kv[5]), pack_bf(kv[6], kv[7]));
      if (c < 2) st_x32(pz, nz(fu(c ? kc[18] : kc[16])));
      TS(5);
    }
    SPLIT();
    WG_WAIT(0);
    packp(p, pw);
#pragma unroll
    for (int u = 0; u < 4; u++) dual_exp(pw + 4 * u, eq + 8 * u);
    SPLIT();
  }
  TS(wg * 16 + 4);
  if (wg == 1) {
    mbar_wait(BAR(MB_UFULL));
    const uint4* ps = g_part + (size_t)hp * 8 * 144 + t;
    const uint32_t* zs = (const uint32_t*)(g_part + (size_t)(hp * 8 + (lane >> 4) * 4) * 144 + 128) + w * 16 + (lane & 15);
    uint4 v[8];
    uint32_t zv[4];
#pragma unroll 1
    for (int it = 0; it < SPIN_MAX; it++) {
#pragma unroll
      for (int i = 0; i < 8; i++) v[i] = ld_x(ps + i * 144);
#pragma unroll
      for (int i = 0; i < 4; i++) zv[i] = ld_x32(zs + i * 576);
      uint32_t m = min(min(zv[0], zv[1]), min(zv[2], zv[3]));
#pragma unroll
      for (int i = 0; i < 8; i++) m = min(m, v[i].x);
      if (__all_sync(0xffffffffu, m != 0)) break;
    }
    float s[8];
    WG_FENCE();
#pragma unroll
    for (int r = 0; r < 8; r++) wgmma_rs_n16(s, v[r], qdesc(sb + OFF_EYE), r);
    WG_COMMIT();
    float zsum = (uf(zv[0]) + uf(zv[1])) + (uf(zv[2]) + uf(zv[3]));
    zsum += __shfl_xor_sync(0xffffffffu, zsum, 16);
    const uint32_t z1 = pack_bf(zsum, 1.f);
    if (lane < 16) sts128(kvs + w * 768 + 512 + lane * 16, z1, z1, z1, z1);
    WG_WAIT(0);
    stsm4(kvs + w * 768 + lane * 16, pack_bf(s[0], s[1]), pack_bf(s[2], s[3]), pack_bf(s[4], s[5]), pack_bf(s[6], s[7]));
    asm volatile("fence.proxy.async.shared::cta;" ::: "memory");
    TS(22);
  }
  nb_sync(NB_KV, 256);
  {
    float n[8][12];
    WG_FENCE();
#pragma unroll
    for (int i = 0; i < 8; i++) wgmma_rs_n24(n[i], make_uint4(eq[4 * i], eq[4 * i + 1], eq[4 * i + 2], eq[4 * i + 3]), qdesc(kvs + (i & 3) * 768), 0);
    WG_COMMIT();
    uint32_t* od = (uint32_t*)(g_o + (size_t)((rt * 4 + wg * 2) * 32 + hp * 2) * 128) + w * 64 + lane;
    WG_WAIT(0);
#pragma unroll
    for (int u = 0; u < 4; u++) {
      float(&np)[12] = n[2 * u];
      const float(&nm)[12] = n[2 * u + 1];
      const float q0 = np[9] * rcp(nm[9]), q1 = np[11] * rcp(nm[11]);
      const float r0 = rcp(fmaf(nm[8], q0, fmaf(np[9], 1e-6f, np[8]))), r1 = rcp(fmaf(nm[10], q1, fmaf(np[11], 1e-6f, np[10])));
#pragma unroll
      for (int i = 0; i < 8; i++) np[i] = fmaf(nm[i], (i & 2) ? q1 : q0, np[i]);
      uint32_t* o = od + (u >> 1) * 16384 + (u & 1) * 512;
      o[0] = pack_bf(np[0] * r0, np[1] * r0);
      o[32] = pack_bf(np[2] * r1, np[3] * r1);
      o[256] = pack_bf(np[4] * r0, np[5] * r0);
      o[288] = pack_bf(np[6] * r1, np[7] * r1);
      if (u == 1) SPLIT();
    }
  }
  TS(wg * 16 + 7);
  nb_arrive(NB_ODONE, 288);
  if (wg) { if (w == 0) TSDUMP(16); return; }
  mbar_wait(BAR(MB_WO));
  mbar_wait(BAR(MB_OA));
  TS(8);
  nb_sync(NB_BDONE, 288);
  TS(9);
  float oc[64];
  {
    constexpr uint64_t ha = mkdesc(0, 0, 128, 0), hb = mkdesc(0, 0, 1024, 1);
    constexpr uint32_t da0 = (uint32_t)mkdesc(stg1, 1024, 0, 0), db0 = (uint32_t)mkdesc(sb + OFF_W, 8192, 0, 0);
#pragma unroll 1
    for (int j = 0; j < 8; j++) {
      const int kb = (j + 7) & 7;
      if ((j & 3) == 1) mbar_spin(j == 1 ? BAR(MB_OC) : BAR(MB_OB));
      WG_FENCE();
#pragma unroll
      for (int k = 0; k < 4; k++) wgmma_ss_n128(oc, ha | (da0 + 512 * kb + 128 * k), hb | (db0 + 1024 * kb + 128 * k), k ? 1 : j);
      WG_COMMIT();
    }
    WG_WAIT(0);
  }
  TS(10);
  const uint32_t ot = ((sb + OFF_T + 1023) & ~1023u) + w * 4096;
#pragma unroll
  for (int hf = 0; hf < 2; hf++) {
#pragma unroll
    for (int i = 8 * hf; i < 8 * hf + 8; i += 2)
      stsm4(ot + hf * 2048 + (lane & 15) * 128 + (((i + (lane >> 4)) ^ lane) & 7) * 16, pack_bf(oc[4 * i], oc[4 * i + 1]),
            pack_bf(oc[4 * i + 2], oc[4 * i + 3]), pack_bf(oc[4 * i + 4], oc[4 * i + 5]), pack_bf(oc[4 * i + 6], oc[4 * i + 7]));
    asm volatile("fence.proxy.async.shared::cta;" ::: "memory");
    __syncwarp();
    e_store2d(&mout, ot + hf * 2048, (hp & 3) * 128 + hf * 64, (rt * 4 + (hp >> 2)) * 64 + w * 16);
  }
  asm volatile(ELECT "cp.async.bulk.commit_group;\n@p cp.async.bulk.wait_group.read 0;\n}\n" ::: "memory");
  TS(wg * 16 + 11);
  GT(61 + wg);
  if (w == 0) TSDUMP(0);
  if (w == 1) TSDUMP(48);
}

typedef CUresult (*EncodeFn)(CUtensorMap*, CUtensorMapDataType, cuuint32_t, void*, const cuuint64_t*, const cuuint64_t*,
                             const cuuint32_t*, const cuuint32_t*, CUtensorMapInterleave, CUtensorMapSwizzle,
                             CUtensorMapL2promotion, CUtensorMapFloatOOBfill);

}

extern "C" void kernel_launch(void* const* d_in, const int* in_sizes, int n_in, void* d_out, int out_size) {
  (void)in_sizes; (void)n_in; (void)out_size;
  void* fn = nullptr;
  cudaDriverEntryPointQueryResult qr;
  cudaGetDriverEntryPoint("cuTensorMapEncodeTiled", &fn, cudaEnableDefault, &qr);
  EncodeFn enc = (EncodeFn)fn;
  CUtensorMap mx, mw, mo, mu, mout, mw4;
  const cuuint32_t es[5] = {1, 1, 1, 1, 1};
  {
    cuuint64_t dims[2] = {512, 2048}, st[1] = {1024};
    cuuint32_t box[2] = {64, 128};
    enc(&mx, CU_TENSOR_MAP_DATA_TYPE_BFLOAT16, 2, d_in[0], dims, st, box, es, CU_TENSOR_MAP_INTERLEAVE_NONE,
        CU_TENSOR_MAP_SWIZZLE_128B, CU_TENSOR_MAP_L2_PROMOTION_L2_128B, CU_TENSOR_MAP_FLOAT_OOB_FILL_NONE);
  }
  {
    cuuint64_t dims[3] = {512, 512, 3}, st[2] = {3072, 1024};
    cuuint32_t box[3] = {32, 64, 3};
    enc(&mw, CU_TENSOR_MAP_DATA_TYPE_BFLOAT16, 3, d_in[1], dims, st, box, es, CU_TENSOR_MAP_INTERLEAVE_NONE,
        CU_TENSOR_MAP_SWIZZLE_64B, CU_TENSOR_MAP_L2_PROMOTION_L2_128B, CU_TENSOR_MAP_FLOAT_OOB_FILL_NONE);
  }
  {
    cuuint64_t dims[3] = {64, 512, 8}, st[2] = {1024, 128};
    cuuint32_t box[3] = {64, 64, 2};
    enc(&mo, CU_TENSOR_MAP_DATA_TYPE_BFLOAT16, 3, d_in[3], dims, st, box, es, CU_TENSOR_MAP_INTERLEAVE_NONE,
        CU_TENSOR_MAP_SWIZZLE_128B, CU_TENSOR_MAP_L2_PROMOTION_L2_128B, CU_TENSOR_MAP_FLOAT_OOB_FILL_NONE);
  }
  {
    cuuint64_t dims[4] = {512, 4, 16, 32}, st[3] = {16384, 1024, 65536};
    cuuint32_t box[4] = {64, 4, 16, 2};
    enc(&mu, CU_TENSOR_MAP_DATA_TYPE_BFLOAT16, 4, d_in[4], dims, st, box, es, CU_TENSOR_MAP_INTERLEAVE_NONE,
        CU_TENSOR_MAP_SWIZZLE_128B, CU_TENSOR_MAP_L2_PROMOTION_L2_128B, CU_TENSOR_MAP_FLOAT_OOB_FILL_NONE);
  }
  {
    cuuint64_t dims[2] = {1024, 2048}, st[1] = {2048};
    cuuint32_t box[2] = {64, 16};
    enc(&mout, CU_TENSOR_MAP_DATA_TYPE_BFLOAT16, 2, d_out, dims, st, box, es, CU_TENSOR_MAP_INTERLEAVE_NONE,
        CU_TENSOR_MAP_SWIZZLE_128B, CU_TENSOR_MAP_L2_PROMOTION_NONE, CU_TENSOR_MAP_FLOAT_OOB_FILL_NONE);
  }
  {
    cuuint64_t dims[4] = {512, 64, 3, 8}, st[3] = {3072, 1024, 64 * 3072};
    cuuint32_t box[4] = {32, 64, 3, 2};
    enc(&mw4, CU_TENSOR_MAP_DATA_TYPE_BFLOAT16, 4, d_in[1], dims, st, box, es, CU_TENSOR_MAP_INTERLEAVE_NONE,
        CU_TENSOR_MAP_SWIZZLE_64B, CU_TENSOR_MAP_L2_PROMOTION_L2_128B, CU_TENSOR_MAP_FLOAT_OOB_FILL_NONE);
  }
  Params P;
  P.x = (const __nv_bfloat16*)d_in[0];
  P.wphi = (const __nv_bfloat16*)d_in[2];
  P.wo = (const __nv_bfloat16*)d_in[3];
  P.logA = (const __nv_bfloat16*)d_in[5];
  P.Aim = (const __nv_bfloat16*)d_in[6];
  P.Cre = (const __nv_bfloat16*)d_in[7];
  P.Cim = (const __nv_bfloat16*)d_in[8];
  P.logdt = (const __nv_bfloat16*)d_in[9];
  P.Dskip = (const __nv_bfloat16*)d_in[10];
  P.out = (__nv_bfloat16*)d_out;
  cudaGetSymbolAddress((void**)&P.xs, g_x);
  P.ts = nullptr;
  cudaFuncSetAttribute(fused_kernel, cudaFuncAttributeMaxDynamicSharedMemorySize, SMEM_BYTES);
  fused_kernel<<<NCTA, NTHREADS, SMEM_BYTES>>>(P, mx, mw, mo, mu, mout, mw4);
}
```

```cpp
#include <cuda_runtime.h>
#include <cuda_bf16.h>
#include <cuda_fp16.h>
#include <cuda.h>
#include <stdint.h>

#define DBG_TS 0

namespace {

constexpr int NTHREADS = 512;
constexpr int NCTA = 128;
constexpr int OFF_W = 0;
constexpr int OFF_X = 98304;
constexpr int OFF_U = OFF_X + 65536;
constexpr int U_CH = 4416, U_ODD = 2240, U_PAD = 128;
constexpr int OFF_STG0 = OFF_U + 18432;
constexpr int SLAB = 3328;
constexpr int OFF_T = OFF_STG0 + 8 * SLAB;
constexpr int T_CH = 5216;
constexpr int T_D = 0;
constexpr int T_5 = 2144;
constexpr int T_3 = T_5 + 384;
constexpr int T_7 = T_5 + 1024;
constexpr int T_9 = T_7 + 320;
constexpr int T_KC = T_9 + 320;
constexpr int T_ST = T_5 - 1024;
constexpr int OFF_PHI = OFF_T + 4 * T_CH;
constexpr int OFF_EYE = OFF_PHI + 1024, OFF_ONE = OFF_EYE + 512;
constexpr int OFF_BAR = OFF_ONE + 256;
constexpr int SMEM_BYTES = OFF_BAR + 512 + 256 * DBG_TS;
constexpr uint32_t SB = 1024;
static_assert(T_KC + 2 * 656 <= T_CH, "table size");
static_assert(SMEM_BYTES <= 232448, "smem");
constexpr int MB_URAW = 0, MB_FULL = 1  , MB_WO = 17, MB_UFULL = 18, MB_OA = 19, MB_OC = 20, MB_OB = 21,
              MB_EMPTY = 22  , MB_AUX = 38;
__host__ __device__ constexpr uint32_t BAR(int i) { return SB + OFF_BAR + 8 * i; }
constexpr int NB_WG0 = 1, NB_ODONE = 2, NB_ST0 = 3  , NB_KV = 5, NB_YZ = 6, NB_INIT = 7, NB_PREP = 8, NB_PROD = 9, NB_KREAD = 10, NB_BDONE = 11, NB_OK = 12  ;
#define X2_AT -1
#define U_AT 2
#define ZERO_STEP 10
constexpr int SPIN_MAX = 1 << 16;

constexpr int X_CNT = 0;
constexpr int X_PART = 256;
constexpr int X_O = X_PART + 16 * 8 * 144;
constexpr int X_Y = X_O + 32 * 32 * 128;
constexpr int X_UT = X_Y + 512 * 8 * 32;
constexpr int X_SIZE = X_UT + 512 * (U_CH / 16);
__device__ __align__(128) uint4 g_x[X_SIZE];
extern __shared__ uint8_t smem_raw[];
#define TS(i) do {} while (0)
#define TS1(i) do {} while (0)
#define GT(i) do {} while (0)
#define TSDUMP(base) do {} while (0)

__device__ __forceinline__ uint32_t smem_u32(const void* p) { return (uint32_t)__cvta_generic_to_shared(p); }
__device__ __forceinline__ void mbar_arrive(uint32_t b) {
  asm volatile("mbarrier.arrive.shared::cta.b64 _, [%0];" ::"r"(b) : "memory");
}
__device__ __forceinline__ void mbar_wait(uint32_t b) {
  uint32_t done = 0;
#pragma unroll 1
  for (int i = 0; i < SPIN_MAX && !done; i++) {
    asm volatile("{\n.reg .pred p;\nmbarrier.try_wait.parity.shared::cta.b64 p, [%1], 0, 4000;\nselp.u32 %0, 1, 0, p;\n}\n"
                 : "=r"(done) : "r"(b) : "memory");
  }
}
__device__ __forceinline__ void mbar_spin(uint32_t b) {
  uint32_t done = 0;
#pragma unroll 1
  for (int i = 0; i < (SPIN_MAX << 4) && !done; i++) {
    asm volatile("{\n.reg .pred p;\nmbarrier.try_wait.parity.shared::cta.b64 p, [%1], 0;\nselp.u32 %0, 1, 0, p;\n}\n"
                 : "=r"(done) : "r"(b) : "memory");
  }
}
__device__ __forceinline__ void mbar_init(uint32_t b, int n) {
  asm volatile("mbarrier.init.shared::cta.b64 [%0], %1;" ::"r"(b), "r"(n) : "memory");
}
__device__ __forceinline__ void mbar_expect(uint32_t b, int bytes) {
  asm volatile("mbarrier.arrive.expect_tx.shared::cta.b64 _, [%0], %1;" ::"r"(b), "r"(bytes) : "memory");
}
__device__ __forceinline__ void nb_sync(int id, int n) { asm volatile("bar.sync %0, %1;" ::"r"(id), "r"(n) : "memory"); }
__device__ __forceinline__ void nb_arrive(int id, int n) { asm volatile("bar.arrive %0, %1;" ::"r"(id), "r"(n) : "memory"); }
#define ELECT "{\n.reg .pred p;\nelect.sync _|p, 0xffffffff;\n@p "
__device__ __forceinline__ void e_arrive(uint32_t b) {
  asm volatile(ELECT "mbarrier.arrive.shared::cta.b64 _, [%0];\n}\n" ::"r"(b) : "memory");
}
__device__ __forceinline__ void e_expect(uint32_t b, int bytes) {
  asm volatile(ELECT "mbarrier.arrive.expect_tx.shared::cta.b64 _, [%0], %1;\n}\n" ::"r"(b), "r"(bytes) : "memory");
}
__device__ __forceinline__ void e_tma2d(uint32_t dst, const CUtensorMap* m, uint32_t bar, int c0, int c1) {
  asm volatile(ELECT "cp.async.bulk.tensor.2d.shared::cluster.global.mbarrier::complete_tx::bytes [%0], [%1, {%3,%4}], [%2];\n}\n"
               ::"r"(dst), "l"(m), "r"(bar), "r"(c0), "r"(c1) : "memory");
}
__device__ __forceinline__ void e_tma3d(uint32_t dst, const CUtensorMap* m, uint32_t bar, int c0, int c1, int c2) {
  asm volatile(ELECT "cp.async.bulk.tensor.3d.shared::cluster.global.mbarrier::complete_tx::bytes [%0], [%1, {%3,%4,%5}], [%2];\n}\n"
               ::"r"(dst), "l"(m), "r"(bar), "r"(c0), "r"(c1), "r"(c2) : "memory");
}
__device__ __forceinline__ void e_tma4d(uint32_t dst, const CUtensorMap* m, uint32_t bar, int c0, int c3) {
  asm volatile(ELECT "cp.async.bulk.tensor.4d.shared::cluster.global.mbarrier::complete_tx::bytes [%0], [%1, {%3,%5,%5,%4}], [%2];\n}\n"
               ::"r"(dst), "l"(m), "r"(bar), "r"(c0), "r"(c3), "r"(0) : "memory");
}
__device__ __forceinline__ void e_bulk(uint32_t dst, const void* src, int bytes, uint32_t bar) {
  asm volatile(ELECT "cp.async.bulk.shared::cluster.global.mbarrier::complete_tx::bytes [%0], [%1], %2, [%3];\n}\n"
               ::"r"(dst), "l"(src), "r"(bytes), "r"(bar) : "memory");
}
__device__ __forceinline__ void e_prefetch(const void* p, int bytes) {
  asm volatile(ELECT "cp.async.bulk.prefetch.L2.global [%0], %1;\n}\n" ::"l"(p), "r"(bytes) : "memory");
}
__device__ __forceinline__ void e_store2d(const CUtensorMap* m, uint32_t src, int c0, int c1) {
  asm volatile(ELECT "cp.async.bulk.tensor.2d.global.shared::cta.bulk_group [%0, {%2,%3}], [%1];\n}\n"
               ::"l"(m), "r"(src), "r"(c0), "r"(c1) : "memory");
}
__host__ __device__ constexpr uint64_t mkdesc(uint32_t addr, uint32_t lbo, uint32_t sbo, int swz) {
  return (uint64_t)((addr & 0x3FFFF) >> 4) | ((uint64_t)(lbo >> 4) << 16) | ((uint64_t)(sbo >> 4) << 32) |
         ((uint64_t)swz << 62);
}
#define SPLIT() asm volatile("{\n.reg .pred p;\nsetp.eq.u32 p, %0, %1;\n@p exit;\n}\n" ::"r"(blockIdx.y), "n"(__LINE__) : "memory")
#define WG_FENCE() asm volatile("wgmma.fence.sync.aligned;" ::: "memory")
#define WG_COMMIT() asm volatile("wgmma.commit_group.sync.aligned;" ::: "memory")
#define WG_WAIT(n) asm volatile("wgmma.wait_group.sync.aligned " #n ";" ::: "memory")

__device__ __forceinline__ void mma(float& d0, float& d1, float& d2, float& d3, uint32_t a0, uint32_t a1, uint32_t a2,
                                    uint32_t a3, uint32_t b0, uint32_t b1) {
  asm volatile("mma.sync.aligned.m16n8k16.row.col.f32.bf16.bf16.f32 {%0,%1,%2,%3},{%4,%5,%6,%7},{%8,%9},{%0,%1,%2,%3};"
               : "+f"(d0), "+f"(d1), "+f"(d2), "+f"(d3)
               : "r"(a0), "r"(a1), "r"(a2), "r"(a3), "r"(b0), "r"(b1));
}
__device__ __forceinline__ void mmac(float (&d)[4], uint32_t a0, uint32_t a1, uint32_t a2, uint32_t a3, uint32_t b0,
                                     uint32_t b1, const float (&c)[4]) {
  asm volatile("mma.sync.aligned.m16n8k16.row.col.f32.bf16.bf16.f32 {%0,%1,%2,%3},{%4,%5,%6,%7},{%8,%9},{%10,%11,%12,%13};"
               : "=f"(d[0]), "=f"(d[1]), "=f"(d[2]), "=f"(d[3])
               : "r"(a0), "r"(a1), "r"(a2), "r"(a3), "r"(b0), "r"(b1), "f"(c[0]), "f"(c[1]), "f"(c[2]), "f"(c[3]));
}
__device__ __forceinline__ void mma_p(int p, float (&d)[4], uint32_t a0, uint32_t a1, uint32_t a2, uint32_t a3, uint32_t b0, uint32_t b1) {
  asm volatile("{\n.reg .pred q;\nsetp.ne.b32 q, %10, 0;\n"
               "@q mma.sync.aligned.m16n8k16.row.col.f32.bf16.bf16.f32 {%0,%1,%2,%3},{%4,%5,%6,%7},{%8,%9},{%0,%1,%2,%3};\n}\n"
               : "+f"(d[0]), "+f"(d[1]), "+f"(d[2]), "+f"(d[3])
               : "r"(a0), "r"(a1), "r"(a2), "r"(a3), "r"(b0), "r"(b1), "r"(p));
}
__device__ __forceinline__ void mmac_p(int p, float (&d)[4], uint32_t a0, uint32_t a1, uint32_t a2, uint32_t a3, uint32_t b0,
                                       uint32_t b1, const float (&c)[4]) {
  asm volatile("{\n.reg .pred q;\nsetp.ne.b32 q, %14, 0;\n"
               "@q mma.sync.aligned.m16n8k16.row.col.f32.bf16.bf16.f32 {%0,%1,%2,%3},{%4,%5,%6,%7},{%8,%9},{%10,%11,%12,%13};\n}\n"
               : "+f"(d[0]), "+f"(d[1]), "+f"(d[2]), "+f"(d[3])
               : "r"(a0), "r"(a1), "r"(a2), "r"(a3), "r"(b0), "r"(b1), "f"(c[0]), "f"(c[1]), "f"(c[2]), "f"(c[3]), "r"(p));
}
__device__ __forceinline__ void mma_h(float (&d)[4], const uint32_t (&a)[4], uint32_t b0, uint32_t b1) {
  asm volatile("mma.sync.aligned.m16n8k16.row.col.f32.f16.f16.f32 {%0,%1,%2,%3},{%4,%5,%6,%7},{%8,%9},{%0,%1,%2,%3};"
               : "+f"(d[0]), "+f"(d[1]), "+f"(d[2]), "+f"(d[3]) : "r"(a[0]), "r"(a[1]), "r"(a[2]), "r"(a[3]), "r"(b0), "r"(b1));
}
__device__ __forceinline__ void mma0(float& d0, float& d1, float& d2, float& d3, uint32_t a0, uint32_t a1, uint32_t a2,
                                     uint32_t a3, uint32_t b0, uint32_t b1) {
  asm volatile("mma.sync.aligned.m16n8k16.row.col.f32.bf16.bf16.f32 {%0,%1,%2,%3},{%4,%5,%6,%7},{%8,%9},{%10,%10,%10,%10};"
               : "=f"(d0), "=f"(d1), "=f"(d2), "=f"(d3)
               : "r"(a0), "r"(a1), "r"(a2), "r"(a3), "r"(b0), "r"(b1), "f"(0.f));
}
__device__ __forceinline__ uint32_t pack_bf(float lo, float hi) {
  uint32_t r;
  asm("cvt.rn.bf16x2.f32 %0, %1, %2;" : "=r"(r) : "f"(hi), "f"(lo));
  return r;
}
__device__ __forceinline__ float bf_lo(uint32_t w) { return __uint_as_float(w << 16); }
__device__ __forceinline__ float bf_hi(uint32_t w) { return __uint_as_float(w & 0xffff0000u); }
__device__ __forceinline__ float bf_round(float x) { return __bfloat162float(__float2bfloat16_rn(x)); }
__device__ __forceinline__ uint32_t bmax2(uint32_t a, uint32_t b) {
  uint32_t r; asm("max.bf16x2 %0, %1, %2;" : "=r"(r) : "r"(a), "r"(b)); return r;
}
__device__ __forceinline__ uint32_t bmin2(uint32_t a, uint32_t b) {
  uint32_t r; asm("min.bf16x2 %0, %1, %2;" : "=r"(r) : "r"(a), "r"(b)); return r;
}
__device__ __forceinline__ float ex2(float x) { float r; asm("ex2.approx.ftz.f32 %0, %1;" : "=f"(r) : "f"(x)); return r; }
__device__ __forceinline__ float rcp(float x) { float r; asm("rcp.approx.ftz.f32 %0, %1;" : "=f"(r) : "f"(x)); return r; }
__device__ __forceinline__ void ldsm4(uint32_t (&r)[4], uint32_t a) {
  asm volatile("ldmatrix.sync.aligned.m8n8.x4.shared.b16 {%0,%1,%2,%3}, [%4];"
               : "=r"(r[0]), "=r"(r[1]), "=r"(r[2]), "=r"(r[3]) : "r"(a) : "memory");
}
__device__ __forceinline__ void ldsm4t(uint32_t (&r)[4], uint32_t a) {
  asm volatile("ldmatrix.sync.aligned.m8n8.x4.trans.shared.b16 {%0,%1,%2,%3}, [%4];"
               : "=r"(r[0]), "=r"(r[1]), "=r"(r[2]), "=r"(r[3]) : "r"(a) : "memory");
}
__device__ __forceinline__ void stsm4(uint32_t a, uint32_t r0, uint32_t r1, uint32_t r2, uint32_t r3) {
  asm volatile("stmatrix.sync.aligned.m8n8.x4.shared.b16 [%0], {%1,%2,%3,%4};"
               ::"r"(a), "r"(r0), "r"(r1), "r"(r2), "r"(r3) : "memory");
}
__device__ __forceinline__ uint32_t lds32(uint32_t a) {
  uint32_t r; asm volatile("ld.shared.u32 %0, [%1];" : "=r"(r) : "r"(a) : "memory"); return r;
}
__device__ __forceinline__ uint32_t lds16(uint32_t a) {
  uint32_t r; asm volatile("{\n.reg .u16 h;\nld.shared.u16 h, [%1];\ncvt.u32.u16 %0, h;\n}\n" : "=r"(r) : "r"(a) : "memory"); return r;
}
__device__ __forceinline__ uint2 lds64(uint32_t a) {
  uint2 r; asm volatile("ld.shared.v2.u32 {%0,%1}, [%2];" : "=r"(r.x), "=r"(r.y) : "r"(a) : "memory"); return r;
}
__device__ __forceinline__ uint4 lds128(uint32_t a) {
  uint4 r;
  asm volatile("ld.shared.v4.u32 {%0,%1,%2,%3}, [%4];" : "=r"(r.x), "=r"(r.y), "=r"(r.z), "=r"(r.w) : "r"(a) : "memory");
  return r;
}
__device__ __forceinline__ void sts32(uint32_t a, uint32_t v) { asm volatile("st.shared.u32 [%0], %1;" ::"r"(a), "r"(v) : "memory"); }
__device__ __forceinline__ void sts16(uint32_t a, uint32_t v) {
  asm volatile("{\n.reg .u16 h;\ncvt.u16.u32 h, %1;\nst.shared.u16 [%0], h;\n}\n" ::"r"(a), "r"(v) : "memory");
}
__device__ __forceinline__ void sts64(uint32_t a, uint32_t x, uint32_t y) {
  asm volatile("st.shared.v2.u32 [%0], {%1,%2};" ::"r"(a), "r"(x), "r"(y) : "memory");
}
__device__ __forceinline__ void sts128(uint32_t a, uint32_t x, uint32_t y, uint32_t z, uint32_t w) {
  asm volatile("st.shared.v4.u32 [%0], {%1,%2,%3,%4};" ::"r"(a), "r"(x), "r"(y), "r"(z), "r"(w) : "memory");
}
__device__ __forceinline__ uint4 ld_x(const uint4* p) {
  uint4 r;
  asm volatile("{\n.reg .b128 t;\nld.relaxed.gpu.global.b128 t, [%4];\nmov.b128 {%0,%1,%2,%3}, t;\n}\n"
               : "=r"(r.x), "=r"(r.y), "=r"(r.z), "=r"(r.w) : "l"(p) : "memory");
  return r;
}
__device__ __forceinline__ uint32_t ld_x32(const uint32_t* p) {
  uint32_t r; asm volatile("ld.relaxed.gpu.global.u32 %0, [%1];" : "=r"(r) : "l"(p) : "memory"); return r;
}
__device__ __forceinline__ void st_x(uint4* p, uint32_t x, uint32_t y, uint32_t z, uint32_t w) {
  asm volatile("{\n.reg .b128 t;\nmov.b128 t, {%1,%2,%3,%4};\nst.relaxed.gpu.global.b128 [%0], t;\n}\n"
               ::"l"(p), "r"(x), "r"(y), "r"(z), "r"(w) : "memory");
}
__device__ __forceinline__ void st_x_p(int p, uint4* a, uint32_t x, uint32_t y, uint32_t z, uint32_t w) {
  asm volatile("{\n.reg .b128 t;\n.reg .pred q;\nsetp.ne.b32 q, %5, 0;\nmov.b128 t, {%1,%2,%3,%4};\n@q st.relaxed.gpu.global.b128 [%0], t;\n}\n"
               ::"l"(a), "r"(x), "r"(y), "r"(z), "r"(w), "r"(p) : "memory");
}
__device__ __forceinline__ void sts64_p(int p, uint32_t a, uint32_t x, uint32_t y) {
  asm volatile("{\n.reg .pred q;\nsetp.ne.b32 q, %3, 0;\n@q st.shared.v2.u32 [%0], {%1,%2};\n}\n" ::"r"(a), "r"(x), "r"(y), "r"(p) : "memory");
}
__device__ __forceinline__ void st_x32(uint32_t* p, uint32_t x) {
  asm volatile("st.relaxed.gpu.global.u32 [%0], %1;" ::"l"(p), "r"(x) : "memory");
}
__device__ __forceinline__ uint32_t nz(uint32_t w) { return max(w, 1u); }
__device__ __forceinline__ uint32_t fu(float x) { return __float_as_uint(x); }
__device__ __forceinline__ float uf(uint32_t x) { return __uint_as_float(x); }

__device__ __forceinline__ void wgmma_ss_n96(float (&d)[48], uint64_t da, uint64_t db, int sc) {
  asm volatile("{\n.reg .pred p;\nsetp.ne.b32 p, %50, 0;\n"
      "wgmma.mma_async.sync.aligned.m64n96k16.f32.bf16.bf16 "
      "{%0,%1,%2,%3,%4,%5,%6,%7,%8,%9,%10,%11,%12,%13,%14,%15,%16,%17,%18,%19,%20,%21,%22,%23,%24,%25,%26,%27,%28,%29,%30,%31,%32,%33,%34,%35,%36,%37,%38,%39,%40,%41,%42,%43,%44,%45,%46,%47}, "
      "%48, %49, p, 1, 1, 0, 1;\n}\n"
      : "+f"(d[0]), "+f"(d[1]), "+f"(d[2]), "+f"(d[3]), "+f"(d[4]), "+f"(d[5]), "+f"(d[6]), "+f"(d[7]),
        "+f"(d[8]), "+f"(d[9]), "+f"(d[10]), "+f"(d[11]), "+f"(d[12]), "+f"(d[13]), "+f"(d[14]), "+f"(d[15]),
        "+f"(d[16]), "+f"(d[17]), "+f"(d[18]), "+f"(d[19]), "+f"(d[20]), "+f"(d[21]), "+f"(d[22]), "+f"(d[23]),
        "+f"(d[24]), "+f"(d[25]), "+f"(d[26]), "+f"(d[27]), "+f"(d[28]), "+f"(d[29]), "+f"(d[30]), "+f"(d[31]),
        "+f"(d[32]), "+f"(d[33]), "+f"(d[34]), "+f"(d[35]), "+f"(d[36]), "+f"(d[37]), "+f"(d[38]), "+f"(d[39]),
        "+f"(d[40]), "+f"(d[41]), "+f"(d[42]), "+f"(d[43]), "+f"(d[44]), "+f"(d[45]), "+f"(d[46]), "+f"(d[47])
      : "l"(da), "l"(db), "r"(sc));
}

__device__ __forceinline__ void wgmma_ss_n128(float (&d)[64], uint64_t da, uint64_t db, int sc) {
  asm volatile("{\n.reg .pred p;\nsetp.ne.b32 p, %66, 0;\n"
      "wgmma.mma_async.sync.aligned.m64n128k16.f32.bf16.bf16 "
      "{%0,%1,%2,%3,%4,%5,%6,%7,%8,%9,%10,%11,%12,%13,%14,%15,%16,%17,%18,%19,%20,%21,%22,%23,%24,%25,%26,%27,%28,%29,%30,%31,%32,%33,%34,%35,%36,%37,%38,%39,%40,%41,%42,%43,%44,%45,%46,%47,%48,%49,%50,%51,%52,%53,%54,%55,%56,%57,%58,%59,%60,%61,%62,%63}, "
      "%64, %65, p, 1, 1, 0, 1;\n}\n"
      : "+f"(d[0]), "+f"(d[1]), "+f"(d[2]), "+f"(d[3]), "+f"(d[4]), "+f"(d[5]), "+f"(d[6]), "+f"(d[7]),
        "+f"(d[8]), "+f"(d[9]), "+f"(d[10]), "+f"(d[11]), "+f"(d[12]), "+f"(d[13]), "+f"(d[14]), "+f"(d[15]),
        "+f"(d[16]), "+f"(d[17]), "+f"(d[18]), "+f"(d[19]), "+f"(d[20]), "+f"(d[21]), "+f"(d[22]), "+f"(d[23]),
        "+f"(d[24]), "+f"(d[25]), "+f"(d[26]), "+f"(d[27]), "+f"(d[28]), "+f"(d[29]), "+f"(d[30]), "+f"(d[31]),
        "+f"(d[32]), "+f"(d[33]), "+f"(d[34]), "+f"(d[35]), "+f"(d[36]), "+f"(d[37]), "+f"(d[38]), "+f"(d[39]),
        "+f"(d[40]), "+f"(d[41]), "+f"(d[42]), "+f"(d[43]), "+f"(d[44]), "+f"(d[45]), "+f"(d[46]), "+f"(d[47]),
        "+f"(d[48]), "+f"(d[49]), "+f"(d[50]), "+f"(d[51]), "+f"(d[52]), "+f"(d[53]), "+f"(d[54]), "+f"(d[55]),
        "+f"(d[56]), "+f"(d[57]), "+f"(d[58]), "+f"(d[59]), "+f"(d[60]), "+f"(d[61]), "+f"(d[62]), "+f"(d[63])
      : "l"(da), "l"(db), "r"(sc));
}

__device__ __forceinline__ void wgmma_ss_n40(float (&d)[20], uint64_t da, uint64_t db, int sc) {
  asm volatile("{\n.reg .pred p;\nsetp.ne.b32 p, %22, 0;\n"
      "wgmma.mma_async.sync.aligned.m64n40k16.f32.bf16.bf16 "
      "{%0,%1,%2,%3,%4,%5,%6,%7,%8,%9,%10,%11,%12,%13,%14,%15,%16,%17,%18,%19}, "
      "%20, %21, p, 1, 1, 1, 1;\n}\n"
      : "+f"(d[0]), "+f"(d[1]), "+f"(d[2]), "+f"(d[3]), "+f"(d[4]), "+f"(d[5]), "+f"(d[6]), "+f"(d[7]),
        "+f"(d[8]), "+f"(d[9]), "+f"(d[10]), "+f"(d[11]), "+f"(d[12]), "+f"(d[13]), "+f"(d[14]), "+f"(d[15]),
        "+f"(d[16]), "+f"(d[17]), "+f"(d[18]), "+f"(d[19])
      : "l"(da), "l"(db), "r"(sc));
}

__device__ __forceinline__ void wgmma_rs_n8(float (&d)[4], const uint4& a, uint64_t db, int sc) {
  asm volatile("{\n.reg .pred p;\nsetp.ne.b32 p, %9, 0;\n"
      "wgmma.mma_async.sync.aligned.m64n8k16.f32.bf16.bf16 "
      "{%0,%1,%2,%3}, "
      "{%4,%5,%6,%7}, %8, p, 1, 1, 1;\n}\n"
      : "+f"(d[0]), "+f"(d[1]), "+f"(d[2]), "+f"(d[3])
      : "r"(a.x), "r"(a.y), "r"(a.z), "r"(a.w), "l"(db), "r"(sc));
}

__device__ __forceinline__ void wgmma_rs_n16(float (&d)[8], const uint4& a, uint64_t db, int sc) {
  asm volatile("{\n.reg .pred p;\nsetp.ne.b32 p, %13, 0;\n"
      "wgmma.mma_async.sync.aligned.m64n16k16.f32.bf16.bf16 "
      "{%0,%1,%2,%3,%4,%5,%6,%7}, "
      "{%8,%9,%10,%11}, %12, p, 1, 1, 1;\n}\n"
      : "+f"(d[0]), "+f"(d[1]), "+f"(d[2]), "+f"(d[3]), "+f"(d[4]), "+f"(d[5]), "+f"(d[6]), "+f"(d[7])
      : "r"(a.x), "r"(a.y), "r"(a.z), "r"(a.w), "l"(db), "r"(sc));
}

__device__ __forceinline__ void wgmma_rs_n24(float (&d)[12], const uint4& a, uint64_t db, int sc) {
  asm volatile("{\n.reg .pred p;\nsetp.ne.b32 p, %17, 0;\n"
      "wgmma.mma_async.sync.aligned.m64n24k16.f32.bf16.bf16 "
      "{%0,%1,%2,%3,%4,%5,%6,%7,%8,%9,%10,%11}, "
      "{%12,%13,%14,%15}, %16, p, 1, 1, 1;\n}\n"
      : "+f"(d[0]), "+f"(d[1]), "+f"(d[2]), "+f"(d[3]), "+f"(d[4]), "+f"(d[5]), "+f"(d[6]), "+f"(d[7]),
        "+f"(d[8]), "+f"(d[9]), "+f"(d[10]), "+f"(d[11])
      : "r"(a.x), "r"(a.y), "r"(a.z), "r"(a.w), "l"(db), "r"(sc));
}

struct Params {
  const __nv_bfloat16 *logA, *Aim, *Cre, *Cim, *logdt, *Dskip, *x, *wphi, *wo;
  __nv_bfloat16* out;
  uint4* xs;
  long long* ts;
};

__device__ __forceinline__ uint4 tr_row(const uint4 (&v)[8], int i) {
  uint32_t o[4];
#pragma unroll
  for (int m = 0; m < 4; m++) {
    const uint4 &ra = v[2 * m], &rb = v[2 * m + 1];
    const int k = i >> 1;
    const uint32_t xa = k == 0 ? ra.x : k == 1 ? ra.y : k == 2 ? ra.z : ra.w;
    const uint32_t xb = k == 0 ? rb.x : k == 1 ? rb.y : k == 2 ? rb.z : rb.w;
    o[m] = __byte_perm(xa, xb, (i & 1) ? 0x7632 : 0x5410);
  }
  return make_uint4(o[0], o[1], o[2], o[3]);
}

struct cpx { float r, i; };
__device__ __forceinline__ cpx csq(cpx a) { return {a.r * a.r - a.i * a.i, 2.f * (a.r * a.i)}; }
__device__ __forceinline__ cpx polar(float e, float t) {
  const float m = ex2(e);
  return {m * __cosf(t), m * __sinf(t)};
}

struct KgenRaw { unsigned short la, ai, cr, ci, ldt; };
__device__ __forceinline__ KgenRaw kgen_load(const Params& P, int d, int unit, int lane) {
  const int o = d * 128 + unit * 32 + lane;
  return {__ldg((const unsigned short*)P.logA + o), __ldg((const unsigned short*)P.Aim + o), __ldg((const unsigned short*)P.Cre + o),
          __ldg((const unsigned short*)P.Cim + o), __ldg((const unsigned short*)P.logdt + d)};
}
struct hmul { __half2 a, b; };
__device__ __forceinline__ hmul mk_mul(cpx w) {
  uint32_t b;
  asm("{\n.reg .f32 n;\nneg.ftz.f32 n, %1;\ncvt.rn.f16x2.f32 %0, %2, n;\n}\n" : "=r"(b) : "f"(w.i), "f"(w.r));
  return {__floats2half2_rn(w.r, w.i), *(const __half2*)&b};
}
__device__ __forceinline__ __half2 hcm(__half2 z, const hmul& w) { return __hfma2(__high2half2(z), w.b, __hmul2(__low2half2(z), w.a)); }
__device__ __forceinline__ uint32_t hu(__half2 v) { return *(const uint32_t*)&v; }

struct KgenAddr { uint32_t sa, sb, lb, lc, la; };
__device__ __forceinline__ KgenAddr kgen_addr(int lane, uint32_t buf) {
  KgenAddr a;
  a.sa = buf + (lane & 7) * 128 + ((((lane >> 3) ^ lane) & 7) << 4);
  a.lb = buf + (lane >> 3) * 128 + (((lane ^ (lane >> 3)) & 7) << 4);
  a.la = buf + ((lane >> 3) & 1) * 1024 + (lane >> 4) * 128 + (((lane ^ (lane >> 4)) & 7) << 4);
  a.sb = a.sa ^ 64; a.lc = a.lb ^ 64;
  asm volatile("" : "+r"(a.sa), "+r"(a.sb), "+r"(a.lb), "+r"(a.lc), "+r"(a.la));
  return a;
}
__device__ __forceinline__ void kgen_unit(const KgenRaw& r, const KgenAddr& ad, uint32_t zero, float (&k)[5][4], float& k2048, float& sc) {
  const float dt = bf_round(expf(bf_lo(r.ldt)));
  const float a2 = bf_round(ex2(bf_lo(r.la) * 1.4426950408889634f)) * (dt * -1.4426950408889634f);
  const float f = bf_lo(r.ai) * dt;
  const float r128 = f * 20.371832715762604f;
  const uint32_t ex = min(max(__reduce_max_sync(0xffffffffu, max(r.cr & 0x7fffu, r.ci & 0x7fffu)) >> 7, 1u), 253u);
  const float cs = uf((254u - ex) << 23);
  sc = 2.f * dt * uf(ex << 23);
  const cpx C = {bf_lo(r.cr) * cs, -bf_lo(r.ci) * cs};
  auto put = [&](const __half2 (&v)[8], uint32_t off) {
    stsm4(ad.sa + off, hu(v[0]), hu(v[1]), hu(v[2]), hu(v[3]));
    stsm4(ad.sb + off, hu(v[4]), hu(v[5]), hu(v[6]), hu(v[7]));
  };
  uint32_t A[4][4], B[5][2][4];
  auto get = [&](int j, uint32_t off) {
    __syncwarp();
    ldsm4(B[j][0], ad.lb + off);
    ldsm4(B[j][1], ad.lc + 512 + off);
  };
  auto tile = [&](int j) {
    k[j][0] = k[j][1] = k[j][2] = k[j][3] = 0.f;
#pragma unroll
    for (int s = 0; s < 4; s++) mma_h(k[j], A[s], B[j][s >> 1][2 * (s & 1)], B[j][s >> 1][2 * (s & 1) + 1]);
  };
  auto after = [&](cpx v, uint32_t dep) { return cpx{uf(fu(v.r) ^ (dep & zero)), v.i}; };
  const cpx w1 = polar(a2, f), w128 = polar(a2 * 128.f, (r128 - rintf(r128)) * 6.283185307179586f);
  const cpx w2 = csq(w1), w4 = csq(w2);
  __half2 t0[8], t1[8], t2[8], t3[8], t4[8];
  const hmul m2 = mk_mul(w2), m4 = mk_mul(w4), m128 = mk_mul(w128);
  t0[0] = __floats2half2_rn(1.f, 0.f); t0[1] = __floats2half2_rn(w1.r, w1.i); t0[2] = m2.a; t0[4] = m4.a;
  t0[3] = hcm(t0[1], m2); t0[5] = hcm(t0[1], m4); t0[6] = hcm(t0[2], m4); t0[7] = hcm(t0[3], m4);
  put(t0, 0); get(0, 0);
  t1[0] = m128.a;
#pragma unroll
  for (int i = 1; i < 8; i++) t1[i] = hcm(t0[i], m128);
  put(t1, 1024); get(1, 1024);
  {
    cpx w8 = csq(after(w4, B[0][0][0]));
    w8.i = -w8.i;
    const cpx w16 = csq(w8), w32 = csq(w16), w64 = csq(w32);
    const hmul m8 = mk_mul(w8), m16 = mk_mul(w16), m32 = mk_mul(w32), m64 = mk_mul(w64);
    __half2 a[8];
    a[0] = __floats2half2_rn(C.r, C.i); a[1] = hcm(a[0], m8);
    a[2] = hcm(a[0], m16); a[3] = hcm(a[1], m16);
#pragma unroll
    for (int i = 0; i < 4; i++) a[4 + i] = hcm(a[i], m32);
    put(a, 0);
#pragma unroll
    for (int i = 0; i < 8; i++) a[i] = hcm(a[i], m64);
    put(a, 1024);
    __syncwarp();
#pragma unroll
    for (int s = 0; s < 4; s++) ldsm4(A[s], (ad.la ^ (s << 5)) + s * 256);
  }
  const cpx w256 = csq(after(w128, B[1][0][0]));
  const hmul m256 = mk_mul(w256);
  t2[0] = m256.a;
#pragma unroll
  for (int i = 1; i < 8; i++) t2[i] = hcm((i & 1) ? t1[i & 6] : t0[i & 6], m256);
  put(t2, 0); get(2, 0);
  tile(0); tile(1);
  const cpx w512 = csq(after(w256, A[0][0]));
  const hmul m512 = mk_mul(w512);
  t3[0] = m512.a;
#pragma unroll
  for (int i = 1; i < 8; i++) t3[i] = hcm((i & 2) ? t2[i & 5] : ((i & 1) ? t1[i & 4] : t0[i & 4]), m512);
  put(t3, 1024); get(3, 1024);
  tile(2);
  const cpx w1024 = csq(after(w512, B[2][0][0])), we = csq(w1024);
  const hmul m1024 = mk_mul(w1024);
  t4[0] = m1024.a;
#pragma unroll
  for (int i = 1; i < 8; i++) t4[i] = hcm((i & 4) ? t3[i & 3] : ((i & 2) ? t2[i & 1] : t1[0]), m1024);
  put(t4, 0); get(4, 0);
  tile(3); tile(4);
  k2048 = (C.r * we.r + C.i * we.i) * sc;
}

__device__ __forceinline__ void build_tables(uint32_t tb, int lane, float (&k)[5][4], float k2048) {
  const int g = lane >> 2, c = lane & 3;
  const uint32_t kc = tb + T_KC + 16;
  {
    const uint32_t a0 = kc + 16 * g + 4 * c, a2 = kc + 2 * (256 + 4 * g + c);
    const uint32_t a3 = kc + 2 * (384 + 2 * g + 64 * (c & 1) + (c >> 1)), a4 = kc + 2 * (512 + g + 32 * c);
#pragma unroll
    for (int r = 0; r < 2; r++) {
      sts32(a0 + 128 * r, pack_bf(k[0][2 * r], k[0][2 * r + 1]));
      sts32(a0 + 128 * r + 256, pack_bf(k[1][2 * r], k[1][2 * r + 1]));
      const uint32_t w2 = pack_bf(k[2][2 * r], k[2][2 * r + 1]);
      const uint32_t w3 = pack_bf(k[3][2 * r], k[3][2 * r + 1]);
      const uint32_t w4 = pack_bf(k[4][2 * r], k[4][2 * r + 1]);
      sts16(a2 + 64 * r, w2); sts16(a2 + 64 * r + 128, w2 >> 16);
      sts16(a3 + 32 * r, w3); sts16(a3 + 32 * r + 64, w3 >> 16);
      sts16(a4 + 16 * r, w4); sts16(a4 + 16 * r + 32, w4 >> 16);
    }
  }
  if (lane == 0) { sts16(kc + 2 * 640, pack_bf(k2048, 0.f)); sts32(kc - 4, 0); }
  __syncwarp();
  const uint32_t td = tb + T_D + 32;
#pragma unroll
  for (int hf = 0; hf < 2; hf++) {
    const uint2 v = lds64(kc + 256 * hf + 8 * lane);
    const uint32_t pv = lds32(kc + 256 * hf + 8 * lane - 4);
    sts128(td + 512 * hf + 16 * lane, __byte_perm(v.x, pv, 0x7610), __byte_perm(v.x, v.x, 0x1032), __byte_perm(v.y, v.x, 0x7610),
           __byte_perm(v.y, v.y, 0x1032));
  }
#pragma unroll
  for (int hf = 0; hf < 2; hf++) {
    const uint32_t v = lds32(kc + 512 + 128 * hf + 4 * lane), nx = lds32(kc + 516 + 128 * hf + 4 * lane);
    uint32_t w0 = __byte_perm(v, v, 0x1010);
    const uint32_t w1 = w0;
    if (hf == 0) { const uint32_t pv = lds32(kc + 508); if (lane == 0) w0 = __byte_perm(v, pv, 0x7610); }
    sts128(td + 1024 + 512 * hf + 16 * lane, w0, w1, __byte_perm(v, v, 0x1032), __byte_perm(nx, v, 0x7610));
  }
  {
    const uint32_t kk = lds16(kc + 2 * 384);
    const uint32_t w = lane < 3 ? (kk | (kk << 16)) : (lane == 3 ? (kk << 16) : 0u);
    if (lane < 24) sts32(td + 4 * (lane < 16 ? 512 + lane : lane - 24), w);
    const uint32_t lo_ = lds16(kc + 2 * 511), le_ = lds16(kc + 2 * 512);
    const uint32_t ja = tb + T_5 + (lane < 16 ? 4 * lane : 256 + 4 * lane);
    sts32(ja, lane == 16 ? (le_ << 16) : 0u);
    sts32(ja + 384, lane == 16 ? (lo_ << 16) : 0u);
    sts32(tb + (lane < 16 ? T_7 : T_9 - 64) + 4 * lane, 0u);
  }
#pragma unroll
  for (int s = 0; s < 2; s++) {
    const uint32_t b = kc + 2 * (s ? 512 : 384) + 8 * lane;
    const uint2 v = lds64(b);
    uint32_t em = lds16(b - 2), e0 = v.x;
    const uint32_t e4 = lds16(b + 8);
    if (lane == 0) { em = 0; e0 = 0; }
    sts64(tb + (s ? T_7 : T_3) + 64 + 8 * lane, __byte_perm(v.x, em, 0x5432), __byte_perm(v.y, v.x, 0x7632));
    sts64(tb + (s ? T_9 : T_5) + 64 + 8 * lane, __byte_perm(v.y, e0, 0x5410), __byte_perm(e4, v.y, 0x5410));
  }
  __syncwarp();
}

__device__ __forceinline__ uint32_t box2w(int lo, int n, int o) {
  return ((unsigned)(o - lo) < (unsigned)n ? 0x3F80u : 0u) | ((unsigned)(o + 1 - lo) < (unsigned)n ? 0x3F800000u : 0u);
}

__device__ __forceinline__ void conv_channel(uint32_t ub, uint32_t tb, int lane, uint4* ydst) {
  const int g = lane >> 2, c = lane & 3, x = g - 2 * c;
  const int mi = lane >> 3;
  const uint32_t qa = ub + U_PAD + 16 * (lane & 7) + ((mi == 0 || mi == 3) ? U_ODD : 0) - (mi == 0 ? 16 : 0);
  const uint32_t hb = ub + U_PAD + (mi & 1) * U_ODD + 16 * ((lane >> 4) + (lane & 7)) - 16;
  const uint32_t kv = lds16(tb + T_KC + 16 + 2 * 512);
  const int oh = c < 2 ? 8 + 2 * c : 2 * c - 8, og = c < 3 ? 2 * c : -10;
  uint32_t bx[4] = {box2w(g - 4, 9, 2 * c), box2w(g - 3, 7, 2 * c), box2w(g - 4, 9, oh), box2w(g - 3, 7, oh)};
  uint32_t by[4] = {box2w(g - 10, 5, 2 * c - 8), box2w(g - 5, 3, 2 * c - 8), box2w(g - 10, 5, og), box2w(g - 5, 3, og)};
  uint32_t lb0 = ((unsigned)(x + 5) < 2u ? kv : 0u) | ((unsigned)(x + 4) < 2u ? kv << 16 : 0u);
  uint32_t lb1 = ((unsigned)(x - 3) < 2u ? kv : 0u) | ((unsigned)(x - 4) < 2u ? kv << 16 : 0u);
  const int q0 = g - 1, q1 = c < 3 ? g : g - 2;
  uint32_t y0a = ub + U_PAD + (q0 & 1) * U_ODD + 16 * (q0 >> 1) + 4 * c;
  uint32_t y1a = ub + U_PAD + (q1 & 1) * U_ODD + 16 * (q1 >> 1) + 4 * c;
#pragma unroll
  for (int i = 0; i < 4; i++) asm volatile("" : "+r"(bx[i]), "+r"(by[i]));
  asm volatile("" : "+r"(lb0), "+r"(lb1), "+r"(y0a), "+r"(y1a));
  mbar_wait(BAR(MB_UFULL));
  mbar_wait(BAR(MB_EMPTY + 15));
  TS(36);
  float acc[16][4];
  {
    uint32_t z09[8], z07[8], zm9[8], zm7[8];
#pragma unroll
    for (int i = 0; i < 8; i++) {
      uint32_t h[4];
      ldsm4(h, hb + 128 * i);
      float y0, y1, y2, y3, w0, w1, w2, w3;
      mma0(y0, y1, y2, y3, bx[0], bx[1], bx[2], bx[3], h[2], c < 2 ? h[3] : h[1]);
      mma0(w0, w1, w2, w3, bx[0], bx[1], bx[2], bx[3], h[1], c < 2 ? h[2] : h[0]);
      z09[i] = pack_bf(y0, y1); z07[i] = pack_bf(y2, y3);
      zm9[i] = pack_bf(w0, w1); zm7[i] = pack_bf(w2, w3);
    }
  uint32_t f3[3][4][4];
  {
    const uint32_t fa = tb + T_7 + 4 * (16 + x);
#pragma unroll
    for (int tt = 0; tt < 3; tt++)
#pragma unroll
      for (int D = 0; D < 4; D++) {
        const uint32_t a = fa + (tt == 0 ? 316 : (tt == 1 ? 320 : 0)) + 64 * D;
        f3[tt][D][0] = lds32(a); f3[tt][D][1] = lds32(a + 32); f3[tt][D][2] = lds32(a - 32); f3[tt][D][3] = lds32(a);
      }
  }
    float a[4][2][4];
#pragma unroll
    for (int kap = 0; kap < 4; kap++)
#pragma unroll
      for (int sg = 0; sg < 2; sg++)
#pragma unroll
        for (int bk = 3; bk >= kap; bk--) {
          const uint32_t(&q0_)[4] = f3[sg ? 2 : 0][bk - kap];
          const uint32_t(&q1_)[4] = f3[sg ? 2 : 1][bk - kap];
          float(&a0)[4] = a[bk][0];
          float(&a1)[4] = a[bk][1];
          if (sg == 0 && kap == 0) {
            mma0(a0[0], a0[1], a0[2], a0[3], q0_[0], q0_[1], q0_[2], q0_[3], z09[0], z09[1]);
            mma0(a1[0], a1[1], a1[2], a1[3], q1_[0], q1_[1], q1_[2], q1_[3], zm9[0], zm9[1]);
          } else {
            mma(a0[0], a0[1], a0[2], a0[3], q0_[0], q0_[1], q0_[2], q0_[3], sg ? zm7[2 * kap] : z09[2 * kap], sg ? zm7[2 * kap + 1] : z09[2 * kap + 1]);
            mma(a1[0], a1[1], a1[2], a1[3], q1_[0], q1_[1], q1_[2], q1_[3], sg ? z07[2 * kap] : zm9[2 * kap], sg ? z07[2 * kap + 1] : zm9[2 * kap + 1]);
          }
        }
    SPLIT();
#pragma unroll
    for (int i = 0; i < 8; i++) {
      uint32_t h[4];
      ldsm4(h, qa + 128 * i);
      const float ci[4] = {a[i >> 1][0][2 * (i & 1)], a[i >> 1][0][2 * (i & 1) + 1], a[i >> 1][1][2 * (i & 1)], a[i >> 1][1][2 * (i & 1) + 1]};
      mmac(acc[8 + i], h[0], h[1], h[2], h[3], lb0, lb1, ci);
    }
  }
  TS(44);
  {
    uint2 a5[10], a3[10];
    const uint32_t aa = tb + T_5 + 4 * (8 + 2 * g - 2 * c);
#pragma unroll
    for (int m = 0; m < 10; m++) { a5[m] = lds64(aa + 32 * m); a3[m] = lds64(aa + 384 + 32 * m); }
    uint32_t x5[12][2], x3[12][2];
    auto ygen = [&](int kap) {
#pragma unroll
      for (int hh = 0; hh < 2; hh++) {
        float y0, y1, y2, y3;
        mma0(y0, y1, y2, y3, by[0], by[1], by[2], by[3], lds32(y0a + 128 * kap + 64 * hh), lds32(y1a + 128 * kap + 64 * hh));
        x5[kap][hh] = pack_bf(y0, y1);
        x3[kap][hh] = pack_bf(y2, y3);
      }
    };
    ygen(11); ygen(10); ygen(9); ygen(8);
#pragma unroll
    for (int kap = 11; kap >= 0; kap--) {
      if (kap >= 4) ygen(kap - 4);
#pragma unroll
      for (int sg = 0; sg < 2; sg++)
#pragma unroll
        for (int i = 4; i >= 0; i--) {
          const int be = kap + 4 + i;
          if (be <= 15) {
            const uint2 &hi = sg ? a3[2 * i + 1] : a5[2 * i + 1], &lo = sg ? a3[2 * i] : a5[2 * i];
            const uint32_t b0 = sg ? x3[kap][0] : x5[kap][0], b1 = sg ? x3[kap][1] : x5[kap][1];
            if (be < 8 && i == 0 && sg == 0) mma0(acc[be][0], acc[be][1], acc[be][2], acc[be][3], hi.x, hi.y, lo.x, lo.y, b0, b1);
            else mma(acc[be][0], acc[be][1], acc[be][2], acc[be][3], hi.x, hi.y, lo.x, lo.y, b0, b1);
          }
        }
    }
  }
  TS(45);
  {
    const uint32_t st = tb + T_ST + lane * 8;
#pragma unroll
    for (int be = 4; be < 12; be++) sts64(st + 256 * be, pack_bf(acc[be][0], acc[be][1]), pack_bf(acc[be][2], acc[be][3]));
    SPLIT();
    uint32_t F[66], qd[8][4];
    const uint32_t fa = tb + T_D + 32 + 4 * x;
#pragma unroll
    for (int i = 0; i < 32; i++) {
      const int s = 120 - (i >> 2) - 8 * (i & 3);
      uint32_t(&q)[4] = qd[i & 7];
      ldsm4(q, qa + 16 * s);
      const int m = 16 * (i & 3) + 2 * (i >> 2);
      F[m] = lds32(fa + 32 * m); F[m + 1] = lds32(fa + 32 * m + 32);
#pragma unroll
      for (int be = 15; be >= 12; be--) {
        const int de = 8 * be - s;
        float(&a)[4] = (be >= 14 && !(i & 1)) ? acc[be - 4] : acc[be];
        if (de >= 0 && be >= 14 && i == 2 * (15 - be)) mma0(a[0], a[1], a[2], a[3], q[0], q[1], q[2], q[3], F[2 * de + 1], F[2 * de]);
        else if (de >= 0) mma(a[0], a[1], a[2], a[3], q[0], q[1], q[2], q[3], F[2 * de + 1], F[2 * de]);
      }
    }
#pragma unroll
    for (int i = 0; i < 8; i++) acc[14 + (i >> 2)][i & 3] += acc[10 + (i >> 2)][i & 3];
    F[64] = lds32(fa + 32 * 64); F[65] = lds32(fa + 32 * 65);
    uint32_t qp = qa + 128 * 11, sta = st + 256 * 10;
    uint4* yd = ydst + 7 * 32;
#pragma unroll
    for (int i = 0; i < 6; i++) ldsm4(qd[i], qp - 16 * i);
    uint2 sv = lds64(sta + 256);
    float ci[4] = {bf_lo(sv.x), bf_hi(sv.x), bf_lo(sv.y), bf_hi(sv.y)};
    float T[5][4];
#pragma unroll
    for (int i = 0; i < 16; i++) T[i >> 2][i & 3] = acc[12 + (i >> 2)][i & 3];
    nb_sync(NB_YZ, 160);
    TS(46);
#pragma unroll 1
    for (int bp = 5; bp >= 0; bp--) {
      uint32_t held[2];
#pragma unroll
      for (int o = 1; o >= 0; o--) {
#pragma unroll
        for (int k = 4; k >= 1; k--) mmac(T[k], qd[0][0], qd[0][1], qd[0][2], qd[0][3], F[16 * k + 1], F[16 * k], T[k - 1]);
        mmac(T[0], qd[0][0], qd[0][1], qd[0][2], qd[0][3], F[1], F[0], ci);
        ldsm4(qd[6], qp - 16 * 6);
        ldsm4(qd[7], qp - 16 * 7);
        sv = lds64(sta);
#pragma unroll
        for (int i = 1; i < 8; i++) {
#pragma unroll
          for (int k = 3; k >= 0; k--)
            mma(T[k][0], T[k][1], T[k][2], T[k][3], qd[i][0], qd[i][1], qd[i][2], qd[i][3], F[16 * k + 2 * i + 1], F[16 * k + 2 * i]);
          if (i < 7) ldsm4(qd[i - 1], qp - 128 - 16 * (i - 1));
          if (i == 2) {
            const uint32_t w0 = pack_bf(T[4][0], T[4][1]), w1 = pack_bf(T[4][2], T[4][3]);
            if (o) { held[0] = w0; held[1] = w1; }
            else st_x(yd, nz(w0), w1, held[0], held[1]);
          }
          if (i == 4) {
            if (2 * bp + o <= 4) sv = make_uint2(0, 0);
            ci[0] = bf_lo(sv.x); ci[1] = bf_hi(sv.x); ci[2] = bf_lo(sv.y); ci[3] = bf_hi(sv.y);
          }
        }
        qp -= 128; sta -= 256;
      }
      yd -= 32;
    }
#pragma unroll
    for (int B = 1; B >= 0; B--)
      st_x(ydst + B * 32, nz(pack_bf(T[2 * B][0], T[2 * B][1])), pack_bf(T[2 * B][2], T[2 * B][3]),
           pack_bf(T[2 * B + 1][0], T[2 * B + 1][1]), pack_bf(T[2 * B + 1][2], T[2 * B + 1][3]));
  }
}

__device__ __forceinline__ void dual_exp(const uint32_t* w, uint32_t* e) {
  const float L = 1.44268798828125f;
  uint32_t mx = bmax2(bmax2(w[0], w[1]), bmax2(w[2], w[3]));
  uint32_t mn = bmin2(bmin2(w[0], w[1]), bmin2(w[2], w[3]));
  mx = bmax2(mx, __shfl_xor_sync(0xffffffffu, mx, 1));
  mn = bmin2(mn, __shfl_xor_sync(0xffffffffu, mn, 1));
  mx = bmax2(mx, __shfl_xor_sync(0xffffffffu, mx, 2));
  mn = bmin2(mn, __shfl_xor_sync(0xffffffffu, mn, 2));
  const float mx0 = bf_lo(mx) * -L, mx1 = bf_hi(mx) * -L, mn0 = bf_lo(mn) * L, mn1 = bf_hi(mn) * L;
#pragma unroll
  for (int i = 0; i < 2; i++) {
    const float a0 = bf_lo(w[2 * i]), a1 = bf_hi(w[2 * i]), b0 = bf_lo(w[2 * i + 1]), b1 = bf_hi(w[2 * i + 1]);
    e[2 * i] = pack_bf(ex2(fmaf(a0, L, mx0)), ex2(fmaf(b0, L, mx0)));
    e[2 * i + 1] = pack_bf(ex2(fmaf(a1, L, mx1)), ex2(fmaf(b1, L, mx1)));
    e[4 + 2 * i] = pack_bf(ex2(fmaf(a0, -L, mn0)), ex2(fmaf(b0, -L, mn0)));
    e[5 + 2 * i] = pack_bf(ex2(fmaf(a1, -L, mn1)), ex2(fmaf(b1, -L, mn1)));
  }
}
__device__ __forceinline__ void normalise(uint32_t* e, const float (&s)[4]) {
  const uint32_t r = pack_bf(rcp(s[0]), rcp(s[2]));
  const __nv_bfloat162 rr = *(const __nv_bfloat162*)&r;
#pragma unroll
  for (int i = 0; i < 4; i++) {
    const __nv_bfloat162 v = __hmul2(*(const __nv_bfloat162*)&e[i], (i & 1) ? __high2bfloat162(rr) : __low2bfloat162(rr));
    e[i] = *(const uint32_t*)&v;
  }
}
__host__ __device__ constexpr uint64_t qdesc(uint32_t addr) { return mkdesc(addr, 128, 256, 0); }

__global__ void __launch_bounds__(NTHREADS, 1)
fused_kernel(const Params P, const __grid_constant__ CUtensorMap mx, const __grid_constant__ CUtensorMap mw,
             const __grid_constant__ CUtensorMap mo, const __grid_constant__ CUtensorMap mu,
             const __grid_constant__ CUtensorMap mout, const __grid_constant__ CUtensorMap mw4) {
  constexpr uint32_t sb = SB;
  const int tid = threadIdx.x, lane = tid & 31;
  const int warp = __shfl_sync(0xffffffffu, tid >> 5, 0);
  const int b = blockIdx.x, oct = b >> 3, i8 = b & 7;
  const int rt = (((oct & 4) ? ~oct : oct) & 3) * 2 + (i8 >> 2);
  const int hp = (oct >> 2) * 4 + (i8 & 3);

  const int wg = warp >> 2, w = warp & 3;
  const int d = b * 4 + ((tid >> 5) & 3);
  const KgenRaw raw = kgen_load(P, d, tid >> 7, lane);
  const unsigned short dsk = __ldg((const unsigned short*)P.Dskip + d);
  if (tid < 384) {
    asm volatile("prefetch.tensormap [%0];" ::"l"(&mu) : "memory");
    asm volatile("prefetch.tensormap [%0];" ::"l"(&mw) : "memory");
    asm volatile("prefetch.tensormap [%0];" ::"l"(&mx) : "memory");
    asm volatile("prefetch.tensormap [%0];" ::"l"(&mw4) : "memory");
  }
  if (warp == 12) {
    if (lane == 0) {
#pragma unroll
      for (int i = 0; i < 9; i++) mbar_init(BAR(i), 1);
      asm volatile("fence.mbarrier_init.release.cluster;" ::: "memory");
    }
    __syncwarp();
    if (lane < 9) mbar_expect(BAR(0) + 8 * lane, (lane == 5 || lane == 7) ? 40960 : ((lane == 0 || lane > 5) ? 16384 : 28672));
    __syncwarp();
    e_tma3d(sb + OFF_W, &mw, BAR(MB_FULL), hp * 32, 0, 0);
    e_tma2d(sb + OFF_X + 3 * 16384, &mx, BAR(MB_FULL), 0, rt * 256);
    nb_arrive(NB_PROD, 192);
  } else if (warp == 14) {
    e_prefetch(P.x + (size_t)(rt * 256 + hp * 8) * 512, 8192);
  } else if (warp == 13) {
    if (lane == 0) {
#pragma unroll
      for (int i = 9; i < 39; i++) mbar_init(BAR(i), i < MB_EMPTY ? 1 : (i < MB_AUX ? 4 : 8));
      asm volatile("fence.mbarrier_init.release.cluster;" ::: "memory");
    }
    __syncwarp();
    if (lane < 9) mbar_expect(BAR(MB_FULL + 8) + 8 * lane, lane < 8 ? 16384 : 131072);
    nb_arrive(NB_PROD, 192);
  }
  const uint32_t tb = sb + OFF_T + w * T_CH;
  const uint32_t kp = wg >= 2 ? sb + OFF_STG0 + 16384 + w * 2048 : ((tb + 127) & ~127u) + wg * 2048;
  const KgenAddr kad = kgen_addr(lane, wg == 3 ? sb + OFF_X + 32768 + w * 2048 : kp);
  if (wg == 1) nb_sync(NB_PROD, 192);
  if (warp == 12) {
#pragma unroll 1
    for (int kb = 1; kb < 4; kb++) {
      if (kb == U_AT) e_tma4d(sb + OFF_STG0, &mu, BAR(MB_URAW), i8 * 64, oct * 2);
      e_tma3d(sb + OFF_W + kb * 12288, &mw, BAR(MB_FULL) + 8 * kb, hp * 32, kb * 64, 0);
      e_tma2d(sb + OFF_X + (kb < 2 ? kb + 3 : kb - 2) * 16384, &mx, BAR(MB_FULL) + 8 * kb, kb * 64, rt * 256);
    }
    e_tma4d(sb + OFF_W + 4 * 12288, &mw4, BAR(MB_FULL + 4), hp * 32, 4);
    e_tma4d(sb + OFF_W + 6 * 12288, &mw4, BAR(MB_FULL + 6), hp * 32, 6);
    if (smem_u32(smem_raw) != SB) __trap();
    if (lane == 0) TS1(54);
  }
  float k[5][4], k2048, ksc;
  kgen_unit(raw, kad, blockIdx.y, k, k2048, ksc);
  TS(40 + wg);
  if ((fu(k[0][0]) & fu(k[1][0]) & fu(k[2][0]) & fu(k[3][0]) & fu(k[4][0])) == 0xffffffffu) sts32(kp, 0);
  if (wg == 3) {
    nb_sync(0, 512);
    if (warp == 12) {
      asm volatile("fence.proxy.async.shared::cta;" ::: "memory");
      e_tma2d(sb + OFF_X + 2 * 16384, &mx, BAR(MB_FULL + 4), 256, rt * 256);
      if (X2_AT < 0) e_prefetch(P.x + (size_t)(rt * 256 + 128 + hp * 8) * 512, 8192);
    }
  } else if (wg) {
    nb_arrive(0, 512);
  }
  k2048 += __shfl_xor_sync(0xffffffffu, k2048, 16);
  k2048 += __shfl_xor_sync(0xffffffffu, k2048, 8);
  if (wg != 2) {
    uint32_t h[10];
#pragma unroll
    for (int j = 0; j < 10; j++) h[j] = hu(__floats2half2_rn(k[j >> 1][2 * (j & 1)], k[j >> 1][2 * (j & 1) + 1]));
    sts128(kp + lane * 16, h[0], h[1], h[2], h[3]);
    sts128(kp + 512 + lane * 16, h[4], h[5], h[6], h[7]);
    sts128(kp + 1024 + lane * 16, h[8], h[9], fu(k2048), fu(ksc));
  }
  if (wg == 0) { nb_arrive(NB_PREP, 512); nb_sync(0, 512); }
  else if (wg != 2) nb_arrive(NB_PREP, 512);
  else nb_sync(NB_PREP, 512);
  if (warp >= 12) {
    asm volatile("setmaxnreg.dec.sync.aligned.u32 32;");
    if (warp == 12) {
      uint32_t slot = sb + OFF_X + 3 * 16384;
#pragma unroll 1
      for (int n = 0; n < 11; n++) {
        mbar_spin(BAR(MB_EMPTY) + 8 * n);
        const int m = n + 5;
        e_tma2d(slot, &mx, BAR(MB_FULL) + 8 * m, (m & 7) * 64, rt * 256 + (m >> 3) * 128);
        slot = slot == sb + OFF_X + 4 * 16384 ? sb + OFF_X : slot + 16384;
        if (n == X2_AT) e_prefetch(P.x + (size_t)(rt * 256 + 128 + hp * 8) * 512, 8192);
        if (n == 7) {
          e_prefetch(P.wo + (size_t)b * 2048, 4096);
          asm volatile("prefetch.tensormap [%0];" ::"l"(&mo) : "memory");
          asm volatile("prefetch.tensormap [%0];" ::"l"(&mout) : "memory");
        }
      }
#pragma unroll 1
      for (int i = 0; i < 8; i++) {
        mbar_wait(BAR(MB_EMPTY + 10) + 8 * ((0x54332100u >> (4 * i)) & 7));
        const int w0 = (0x54736210u >> (4 * i)) & 7;
        e_tma3d(sb + OFF_W + w0 * 16384, &mo, BAR(MB_WO), 0, w0 * 64, (hp & 3) * 2);
      }
    } else {
      if (warp == 15) {
        const uint4 v0 = __ldg((const uint4*)P.wphi + hp * 64 + lane), v1 = __ldg((const uint4*)P.wphi + hp * 64 + 32 + lane);
        sts128(sb + OFF_PHI + (lane & 1) * 256 + (lane >> 1) * 16, v0.x, v0.y, v0.z, v0.w);
        sts128(sb + OFF_PHI + 512 + (lane & 1) * 256 + (lane >> 1) * 16, v1.x, v1.y, v1.z, v1.w);
        const uint32_t one = (((lane >> 3) ^ (lane >> 4)) & 1) ? 0u : ((lane & 1) ? 0x3F800000u : 0x3F80u);
        const int q = (lane >> 1) & 3;
        sts128(sb + OFF_EYE + lane * 16, q == 0 ? one : 0u, q == 1 ? one : 0u, q == 2 ? one : 0u, q == 3 ? one : 0u);
        sts64(sb + OFF_ONE + lane * 8, 0x3F803F80u, 0x3F803F80u);
        asm volatile("fence.proxy.async.shared::cta;" ::: "memory");
        nb_arrive(NB_KREAD, 160);
      }
      uint32_t* cnt = (uint32_t*)(P.xs + X_CNT) + (warp == 13 ? i8 : (warp == 14 ? 8 + rt : 16 + (rt >> 1))) * 32;
      const unsigned target = (ld_x32(cnt) & ~31u) + 32;
      if (warp == 13) {
        uint4* pz = P.xs + X_PART + (hp * 8 + rt) * 144 + lane;
#pragma unroll 1
        for (int i = 144 - lane; i > 0; i -= 32, pz += 32) st_x(pz, 0, 0, 0, 0);
        nb_sync(NB_INIT, 160);
      } else if (warp == 15) {
        mbar_wait(BAR(MB_EMPTY + ZERO_STEP));
        uint4* py = P.xs + X_Y + b * 1024 + lane;
        uint4* po = P.xs + X_O + (rt * 4 * 32 + hp * 2) * 128 + lane;
#pragma unroll 1
        for (int i = 0; i < 1024; i += 32) {
          st_x(po + (i >> 8) * 4096 + (i & 255), 0, 0, 0, 0);
          st_x(py + i, 0, 0, 0, 0);
        }
        __syncwarp();
      } else {
        nb_sync(NB_ODONE, 288);
      }
      if (lane == 0) {
        if (warp == 14) asm volatile("red.relaxed.gpu.global.add.u32 [%0], 2;" ::"l"(cnt) : "memory");
        else asm volatile("red.release.gpu.global.add.u32 [%0], %1;" ::"l"(cnt), "r"(warp == 15 ? 1 : 2) : "memory");
      }
      if (lane == 0) TS1(warp == 13 ? 50 : (warp == 14 ? 57 : 53));
      asm volatile("fence.proxy.async.shared::cta;" ::: "memory");
      if (warp == 13) cnt += ((lane & 1 ? b >> 4 : i8 ^ (lane & 4)) - i8) * 32;
#pragma unroll 1
      for (int i = 0; i < SPIN_MAX; i++) {
        unsigned v;
        asm volatile("ld.acquire.gpu.global.u32 %0, [%1];" : "=r"(v) : "l"(cnt) : "memory");
        if (__all_sync(0xffffffffu, (int)(v - target) >= 0)) break;
      }
      if (lane == 0) TS1(warp == 13 ? 51 : (warp == 14 ? 58 : 55));
      if (warp == 15) { nb_arrive(NB_YZ, 160); nb_arrive(NB_KV, 288); return; }
      asm volatile("fence.proxy.async.global;" ::: "memory");
      if (warp == 13) {
        mbar_wait(BAR(MB_EMPTY + 11));
        e_expect(BAR(MB_UFULL), 4 * U_CH);
        e_bulk(sb + OFF_U, P.xs + X_UT + b * (U_CH / 4), 4 * U_CH, BAR(MB_UFULL));
      } else {
        const uint4* src = P.xs + X_O + (rt * 4 + (hp >> 2)) * 4096;
        e_expect(BAR(MB_OA), 14336);
        e_bulk(sb + OFF_STG0, src + 3200, 14336, BAR(MB_OA));
        e_expect(BAR(MB_OC), 32768);
        e_bulk(sb + OFF_X + 32768, src, 32768, BAR(MB_OC));
        nb_sync(NB_BDONE, 288);
        asm volatile("fence.proxy.async.shared::cta;" ::: "memory");
        e_expect(BAR(MB_OB), 18432);
        e_bulk(sb + OFF_U, src + 2048, 18432, BAR(MB_OB));
      }
    }
    return;
  }

  const int t = tid & 127;
  const int g = lane >> 2, c = lane & 3;
  {
    if (wg == 2) {
      asm volatile("setmaxnreg.inc.sync.aligned.u32 160;");
#pragma unroll
      for (int j = 0; j < 5; j++) { k[j][0] *= ksc; k[j][1] *= ksc; k[j][2] *= ksc; k[j][3] *= ksc; }
#pragma unroll 1
      for (int q = 0; q < 3; q++) {
        const uint32_t src = (q == 2 ? kp : ((tb + 127) & ~127u) + q * 2048) + lane * 16;
        const uint4 v0 = lds128(src), v1 = lds128(src + 512), v2 = lds128(src + 1024);
        const uint32_t h[10] = {v0.x, v0.y, v0.z, v0.w, v1.x, v1.y, v1.z, v1.w, v2.x, v2.y};
#pragma unroll
        for (int j = 0; j < 10; j++) {
          const float2 f = __half22float2(*(const __half2*)&h[j]);
          k[j >> 1][2 * (j & 1)] = fmaf(f.x, uf(v2.w), k[j >> 1][2 * (j & 1)]);
          k[j >> 1][2 * (j & 1) + 1] = fmaf(f.y, uf(v2.w), k[j >> 1][2 * (j & 1) + 1]);
        }
        k2048 += uf(v2.z);
      }
#pragma unroll
      for (int o2 = 4; o2; o2 >>= 1) k2048 += __shfl_xor_sync(0xffffffffu, k2048, o2);
      if (lane == 0) k[0][0] += bf_lo(dsk);
      __syncwarp();
      if (lane == 0) mbar_arrive(BAR(MB_AUX));
      TS(34);
      build_tables(tb, lane, k, k2048);
      TS(35);
      uint4* const g_y = P.xs + X_Y;
      conv_channel(sb + OFF_U + w * U_CH, tb, lane, g_y + (size_t)d * 256 + lane);
      nb_arrive(NB_BDONE, 288);
      TS(37);
      const int lam = w * 8 + g;
      const uint4* src = g_y + (size_t)(oct * 32 + c * 8) * 256 + i8 * 32 + lam;
      uint4 v[8];
#pragma unroll 1
      for (int it = 0; it < SPIN_MAX; it++) {
        uint32_t m = 0xffffffffu;
#pragma unroll
        for (int i = 0; i < 8; i++) v[i] = ld_x(src + i * 256);
#pragma unroll
        for (int i = 0; i < 8; i++) m = min(m, v[i].x);
        if (__all_sync(0xffffffffu, m != 0)) break;
      }
      __nv_bfloat16* dst = P.out + (size_t)(i8 * 256 + (lam >> 2) * 16 + (lam & 3) * 2) * 1024 + 512 + oct * 32 + c * 8;
#pragma unroll
      for (int i = 0; i < 8; i++) *(uint4*)(dst + (size_t)((i >> 2) * 128 + ((i >> 1) & 1) * 8 + (i & 1)) * 1024) = tr_row(v, i);
      TS(38);
      GT(63);
      if (w == 0) TSDUMP(32);
      return;
    }
    if (wg == 1) {
      mbar_wait(BAR(MB_URAW));
      TS(48);
      uint4* dst = P.xs + X_UT + (i8 * 64 + g) * (U_CH / 16) + (w & 1) * (U_ODD / 16) + U_PAD / 16 + oct * 8 + (w >> 1) * 4 + c;
      const int ln = ((lane >> 1) & 3) + 4 * (lane & 1);
      uint32_t r[8][4];
#pragma unroll
      for (int i = 0; i < 8; i++) ldsm4t(r[i], sb + OFF_STG0 + w * 4096 + ((lane >> 3) * 8 + ln) * 128 + ((i ^ ln) << 4));
#pragma unroll
      for (int i = 0; i < 8; i++) dst[i * (U_CH / 2)] = make_uint4(r[i][0], r[i][1], r[i][2], r[i][3]);
      nb_arrive(NB_INIT, 160);
      if (lane == 0) mbar_arrive(BAR(MB_AUX));
      mbar_wait(BAR(MB_EMPTY + 4));
      mbar_spin(BAR(MB_EMPTY + 6));
    }
    TS(wg * 16 + 1);
  }

  float acc[2][48];
  {
    uint32_t fb = BAR(MB_FULL) + 64 * wg;
    uint32_t da = (uint32_t)mkdesc(sb + OFF_X, 16, 0, 0) + (wg ? 1024 : 3072), db = (uint32_t)mkdesc(sb + OFF_W, 4096, 0, 0);
    constexpr uint64_t ha = mkdesc(0, 0, 1024, 1), hb = mkdesc(0, 0, 512, 2);
    mbar_spin(fb);
    TS(wg * 16 + 2);
#pragma unroll 1
    for (int kb = 0; kb < 8; kb++) {
      WG_FENCE();
#pragma unroll
      for (int k = 0; k < 4; k++) {
        wgmma_ss_n96(acc[0], ha | (da + 2 * k), hb | (db + 64 * k), k ? 1 : kb);
        wgmma_ss_n96(acc[1], ha | (da + 2 * k + 512), hb | (db + 64 * k), k ? 1 : kb);
      }
      WG_COMMIT();
      if (kb < 7) mbar_spin(fb + 8);
      WG_WAIT(1);
      if (kb > 0) e_arrive(fb + 8 * (MB_EMPTY - MB_FULL - 1));
      fb += 8; db += 768;
      da = da == (uint32_t)mkdesc(sb + OFF_X + 65536, 16, 0, 0) ? da - 4096 : da + 1024;
    }
    if (wg == 0) nb_sync(NB_KREAD, 160);
    WG_WAIT(0);
    e_arrive(fb + 8 * (MB_EMPTY - MB_FULL - 1));
    mbar_spin(fb + 8 * (MB_EMPTY - MB_FULL - 1));
  }
  TS(wg * 16 + 3);
  asm volatile("setmaxnreg.inc.sync.aligned.u32 160;");

  constexpr uint32_t stg0 = sb + OFF_STG0, stg1 = sb + OFF_X + 32768;
  uint4* const g_part = P.xs + X_PART;
  uint4* const g_o = P.xs + X_O;
  constexpr uint32_t kvs = stg0;
  auto pack8 = [](const float* a) { return make_uint4(pack_bf(a[0], a[1]), pack_bf(a[2], a[3]), pack_bf(a[4], a[5]), pack_bf(a[6], a[7])); };
  auto feat = [&](const uint4 (&af)[4], float (&p)[4][8]) {
    WG_FENCE();
#pragma unroll
    for (int u = 0; u < 4; u++) wgmma_rs_n16(p[u], af[u], qdesc(sb + OFF_PHI + (u & 1) * 512), 0);
    WG_COMMIT();
  };
  auto packp = [](const float (&p)[4][8], uint32_t (&pw)[16]) {
#pragma unroll
    for (int i = 0; i < 16; i++) pw[i] = pack_bf(p[i >> 2][(i & 1) + 2 * (i & 2)], p[i >> 2][(i & 1) + 2 * (i & 2) + 2]);
  };
  auto contract = [&](float (&kc)[20], uint32_t stg, int acc_in) {
    WG_FENCE();
#pragma unroll
    for (int s = 0; s < 8; s++) wgmma_ss_n40(kc, qdesc(stg + s * SLAB), qdesc(stg + s * SLAB + 2048), s ? 1 : acc_in);
    WG_COMMIT();
    WG_WAIT(0);
  };
  uint32_t eq[32];
  {
    uint4 af[4], aq[4], vp[4];
    float p[4][8];
#pragma unroll
    for (int u = 0; u < 4; u++) af[u] = pack8(acc[u >> 1] + 16 + 8 * (u & 1));
    feat(af, p);
#pragma unroll
    for (int u = 0; u < 4; u++) { aq[u] = pack8(acc[u >> 1] + 8 * (u & 1)); vp[u] = pack8(acc[u >> 1] + 32 + 8 * (u & 1)); }
    WG_WAIT(0);
    uint32_t pw[16], ek[32];
    packp(p, pw);
#pragma unroll
    for (int u = 0; u < 4; u++) dual_exp(pw + 4 * u, ek + 8 * u);
    TS(wg * 16 + 12);
    mbar_wait(BAR(MB_AUX));
    float rs[8][4];
    WG_FENCE();
#pragma unroll
    for (int i = 0; i < 8; i++) wgmma_rs_n8(rs[i], make_uint4(ek[4 * i], ek[4 * i + 1], ek[4 * i + 2], ek[4 * i + 3]), qdesc(sb + OFF_ONE), 0);
    WG_COMMIT();
    feat(aq, p);
    const uint32_t sl = (wg ? stg1 : stg0) + w * SLAB + lane * 16;
#pragma unroll
    for (int i = 0; i < 4; i++) stsm4(sl + (i >> 1) * 4 * SLAB + 2048 + (i & 1) * 512, vp[i].x, vp[i].y, vp[i].z, vp[i].w);
    sts128(sl + (lane >> 4) * (4 * SLAB - 256) + 3072, 0x3F803F80u, 0x3F803F80u, 0x3F803F80u, 0x3F803F80u);
    WG_WAIT(1);
#pragma unroll
    for (int i = 0; i < 8; i++) {
      normalise(ek + 4 * i, rs[i]);
      stsm4(sl + (i >> 2) * 4 * SLAB + (i & 3) * 512, ek[4 * i], ek[4 * i + 1], ek[4 * i + 2], ek[4 * i + 3]);
    }
    asm volatile("fence.proxy.async.shared::cta;" ::: "memory");
    TS(wg * 16 + 13);
    if (wg) {
      nb_arrive(NB_ST0, 256);
    } else {
      float kc[20];
      uint4* pp = g_part + (size_t)(hp * 8 + rt) * 144 + t;
      uint32_t* pz = (uint32_t*)(pp - t + 128) + w * 16 + c * 8 + g;
      asm volatile("" : "+l"(pp), "+l"(pz));
      nb_sync(NB_WG0, 128);
      contract(kc, stg0, 0);
      mbar_wait(BAR(MB_UFULL));
      TS(15);
      nb_sync(NB_ST0, 256);
      contract(kc, stg1, 1);
      TS(6);
      float kv[8];
#pragma unroll
      for (int i = 0; i < 8; i++) kv[i] = w & 2 ? kc[8 + i] : kc[i];
      st_x(pp, nz(pack_bf(kv[0], kv[1])), pack_bf(kv[2], kv[3]), pack_bf(kv[4], kv[5]), pack_bf(kv[6], kv[7]));
      if (c < 2) st_x32(pz, nz(fu(c ? kc[18] : kc[16])));
      TS(5);
    }
    SPLIT();
    WG_WAIT(0);
    packp(p, pw);
#pragma unroll
    for (int u = 0; u < 4; u++) dual_exp(pw + 4 * u, eq + 8 * u);
    SPLIT();
  }
  TS(wg * 16 + 4);
  if (wg == 1) {
    mbar_wait(BAR(MB_UFULL));
    const uint4* ps = g_part + (size_t)hp * 8 * 144 + t;
    const uint32_t* zs = (const uint32_t*)(g_part + (size_t)(hp * 8 + (lane >> 4) * 4) * 144 + 128) + w * 16 + (lane & 15);
    uint4 v[8];
    uint32_t zv[4];
#pragma unroll 1
    for (int it = 0; it < SPIN_MAX; it++) {
#pragma unroll
      for (int i = 0; i < 8; i++) v[i] = ld_x(ps + i * 144);
#pragma unroll
      for (int i = 0; i < 4; i++) zv[i] = ld_x32(zs + i * 576);
      uint32_t m = min(min(zv[0], zv[1]), min(zv[2], zv[3]));
#pragma unroll
      for (int i = 0; i < 8; i++) m = min(m, v[i].x);
      if (__all_sync(0xffffffffu, m != 0)) break;
    }
    float s[8];
    WG_FENCE();
#pragma unroll
    for (int r = 0; r < 8; r++) wgmma_rs_n16(s, v[r], qdesc(sb + OFF_EYE), r);
    WG_COMMIT();
    float zsum = (uf(zv[0]) + uf(zv[1])) + (uf(zv[2]) + uf(zv[3]));
    zsum += __shfl_xor_sync(0xffffffffu, zsum, 16);
    const uint32_t z1 = pack_bf(zsum, 1.f);
    if (lane < 16) sts128(kvs + w * 768 + 512 + lane * 16, z1, z1, z1, z1);
    WG_WAIT(0);
    stsm4(kvs + w * 768 + lane * 16, pack_bf(s[0], s[1]), pack_bf(s[2], s[3]), pack_bf(s[4], s[5]), pack_bf(s[6], s[7]));
    asm volatile("fence.proxy.async.shared::cta;" ::: "memory");
    TS(22);
  }
  nb_sync(NB_KV, 288);
  {
    float n[8][12];
    WG_FENCE();
#pragma unroll
    for (int i = 0; i < 8; i++) wgmma_rs_n24(n[i], make_uint4(eq[4 * i], eq[4 * i + 1], eq[4 * i + 2], eq[4 * i + 3]), qdesc(kvs + (i & 3) * 768), 0);
    WG_COMMIT();
    uint32_t* od = (uint32_t*)(g_o + (size_t)((rt * 4 + wg * 2) * 32 + hp * 2) * 128) + w * 64 + lane;
    WG_WAIT(0);
#pragma unroll
    for (int u = 0; u < 4; u++) {
      float(&np)[12] = n[2 * u];
      const float(&nm)[12] = n[2 * u + 1];
      const float q0 = np[9] * rcp(nm[9]), q1 = np[11] * rcp(nm[11]);
      const float r0 = rcp(fmaf(nm[8], q0, fmaf(np[9], 1e-6f, np[8]))), r1 = rcp(fmaf(nm[10], q1, fmaf(np[11], 1e-6f, np[10])));
#pragma unroll
      for (int i = 0; i < 8; i++) np[i] = fmaf(nm[i], (i & 2) ? q1 : q0, np[i]);
      uint32_t* o = od + (u >> 1) * 16384 + (u & 1) * 512;
      st_x32(o + 0, nz(pack_bf(np[0] * r0, np[1] * r0)));
      st_x32(o + 32, nz(pack_bf(np[2] * r1, np[3] * r1)));
      st_x32(o + 256, nz(pack_bf(np[4] * r0, np[5] * r0)));
      st_x32(o + 288, nz(pack_bf(np[6] * r1, np[7] * r1)));
      if (u == 1) SPLIT();
    }
  }
  TS(wg * 16 + 7);
  nb_arrive(NB_ODONE, 288);
  if (wg) {
    const uint4* src = g_o + (rt * 4 + (hp >> 2)) * 4096;
#pragma unroll 1
    for (int pc = 0; pc < 3; pc++) {
      const int lo = pc == 0 ? 51200 : (pc == 1 ? 0 : 32768), hi = pc == 0 ? 65536 : (pc == 1 ? 32768 : 51200);
      mbar_wait(BAR(MB_OA) + 8 * pc);
      uint32_t m = 0xffffffffu;
#pragma unroll 4
      for (int a = lo + t * 32; a < hi; a += 4096) m = min(m, lds32(stg1 + a + (lane >> 2) * 4));
      if (__any_sync(0xffffffffu, m == 0)) {
#pragma unroll 1
        for (int a = lo + t * 32; a < hi; a += (a & 16) ? 4080 : 16) {
          uint4 v;
#pragma unroll 1
          for (int it = 0; it < SPIN_MAX; it++) {
            asm volatile("ld.relaxed.gpu.global.v4.u32 {%0,%1,%2,%3}, [%4];" : "=r"(v.x), "=r"(v.y), "=r"(v.z), "=r"(v.w) : "l"(src + (a >> 4)) : "memory");
            if (min(min(v.x, v.y), min(v.z, v.w)) != 0) break;
          }
          sts128(stg1 + a, v.x, v.y, v.z, v.w);
        }
        asm volatile("fence.proxy.async.shared::cta;" ::: "memory");
      }
      nb_arrive(NB_OK + pc, 256);
    }
    if (w == 0) TSDUMP(16);
    return;
  }
  mbar_wait(BAR(MB_WO));
  nb_sync(NB_OK, 256);
  TS(8);
  nb_sync(NB_BDONE, 288);
  TS(9);
  float oc[64];
  {
    constexpr uint64_t ha = mkdesc(0, 0, 128, 0), hb = mkdesc(0, 0, 1024, 1);
    constexpr uint32_t da0 = (uint32_t)mkdesc(stg1, 1024, 0, 0), db0 = (uint32_t)mkdesc(sb + OFF_W, 8192, 0, 0);
#pragma unroll 1
    for (int j = 0; j < 8; j++) {
      const int kb = (j + 7) & 7;
      if ((j & 3) == 1) nb_sync(NB_OK + 1 + (j >> 2), 256);
      WG_FENCE();
#pragma unroll
      for (int k = 0; k < 4; k++) wgmma_ss_n128(oc, ha | (da0 + 512 * kb + 128 * k), hb | (db0 + 1024 * kb + 128 * k), k ? 1 : j);
      WG_COMMIT();
    }
    WG_WAIT(0);
  }
  TS(10);
  const uint32_t ot = ((sb + OFF_T + 1023) & ~1023u) + w * 4096;
#pragma unroll
  for (int hf = 0; hf < 2; hf++) {
#pragma unroll
    for (int i = 8 * hf; i < 8 * hf + 8; i += 2)
      stsm4(ot + hf * 2048 + (lane & 15) * 128 + (((i + (lane >> 4)) ^ lane) & 7) * 16, pack_bf(oc[4 * i], oc[4 * i + 1]),
            pack_bf(oc[4 * i + 2], oc[4 * i + 3]), pack_bf(oc[4 * i + 4], oc[4 * i + 5]), pack_bf(oc[4 * i + 6], oc[4 * i + 7]));
    asm volatile("fence.proxy.async.shared::cta;" ::: "memory");
    __syncwarp();
    e_store2d(&mout, ot + hf * 2048, (hp & 3) * 128 + hf * 64, (rt * 4 + (hp >> 2)) * 64 + w * 16);
  }
  asm volatile(ELECT "cp.async.bulk.commit_group;\n@p cp.async.bulk.wait_group.read 0;\n}\n" ::: "memory");
  TS(wg * 16 + 11);
  GT(61 + wg);
  if (w == 0) TSDUMP(0);
  if (w == 1) TSDUMP(48);
}

typedef CUresult (*EncodeFn)(CUtensorMap*, CUtensorMapDataType, cuuint32_t, void*, const cuuint64_t*, const cuuint64_t*,
                             const cuuint32_t*, const cuuint32_t*, CUtensorMapInterleave, CUtensorMapSwizzle,
                             CUtensorMapL2promotion, CUtensorMapFloatOOBfill);

}

extern "C" void kernel_launch(void* const* d_in, const int* in_sizes, int n_in, void* d_out, int out_size) {
  (void)in_sizes; (void)n_in; (void)out_size;
  void* fn = nullptr;
  cudaDriverEntryPointQueryResult qr;
  cudaGetDriverEntryPoint("cuTensorMapEncodeTiled", &fn, cudaEnableDefault, &qr);
  EncodeFn enc = (EncodeFn)fn;
  CUtensorMap mx, mw, mo, mu, mout, mw4;
  const cuuint32_t es[5] = {1, 1, 1, 1, 1};
  {
    cuuint64_t dims[2] = {512, 2048}, st[1] = {1024};
    cuuint32_t box[2] = {64, 128};
    enc(&mx, CU_TENSOR_MAP_DATA_TYPE_BFLOAT16, 2, d_in[0], dims, st, box, es, CU_TENSOR_MAP_INTERLEAVE_NONE,
        CU_TENSOR_MAP_SWIZZLE_128B, CU_TENSOR_MAP_L2_PROMOTION_L2_128B, CU_TENSOR_MAP_FLOAT_OOB_FILL_NONE);
  }
  {
    cuuint64_t dims[3] = {512, 512, 3}, st[2] = {3072, 1024};
    cuuint32_t box[3] = {32, 64, 3};
    enc(&mw, CU_TENSOR_MAP_DATA_TYPE_BFLOAT16, 3, d_in[1], dims, st, box, es, CU_TENSOR_MAP_INTERLEAVE_NONE,
        CU_TENSOR_MAP_SWIZZLE_64B, CU_TENSOR_MAP_L2_PROMOTION_L2_128B, CU_TENSOR_MAP_FLOAT_OOB_FILL_NONE);
  }
  {
    cuuint64_t dims[3] = {64, 512, 8}, st[2] = {1024, 128};
    cuuint32_t box[3] = {64, 64, 2};
    enc(&mo, CU_TENSOR_MAP_DATA_TYPE_BFLOAT16, 3, d_in[3], dims, st, box, es, CU_TENSOR_MAP_INTERLEAVE_NONE,
        CU_TENSOR_MAP_SWIZZLE_128B, CU_TENSOR_MAP_L2_PROMOTION_L2_128B, CU_TENSOR_MAP_FLOAT_OOB_FILL_NONE);
  }
  {
    cuuint64_t dims[4] = {512, 4, 16, 32}, st[3] = {16384, 1024, 65536};
    cuuint32_t box[4] = {64, 4, 16, 2};
    enc(&mu, CU_TENSOR_MAP_DATA_TYPE_BFLOAT16, 4, d_in[4], dims, st, box, es, CU_TENSOR_MAP_INTERLEAVE_NONE,
        CU_TENSOR_MAP_SWIZZLE_128B, CU_TENSOR_MAP_L2_PROMOTION_L2_128B, CU_TENSOR_MAP_FLOAT_OOB_FILL_NONE);
  }
  {
    cuuint64_t dims[2] = {1024, 2048}, st[1] = {2048};
    cuuint32_t box[2] = {64, 16};
    enc(&mout, CU_TENSOR_MAP_DATA_TYPE_BFLOAT16, 2, d_out, dims, st, box, es, CU_TENSOR_MAP_INTERLEAVE_NONE,
        CU_TENSOR_MAP_SWIZZLE_128B, CU_TENSOR_MAP_L2_PROMOTION_NONE, CU_TENSOR_MAP_FLOAT_OOB_FILL_NONE);
  }
  {
    cuuint64_t dims[4] = {512, 64, 3, 8}, st[3] = {3072, 1024, 64 * 3072};
    cuuint32_t box[4] = {32, 64, 3, 2};
    enc(&mw4, CU_TENSOR_MAP_DATA_TYPE_BFLOAT16, 4, d_in[1], dims, st, box, es, CU_TENSOR_MAP_INTERLEAVE_NONE,
        CU_TENSOR_MAP_SWIZZLE_64B, CU_TENSOR_MAP_L2_PROMOTION_L2_128B, CU_TENSOR_MAP_FLOAT_OOB_FILL_NONE);
  }
  Params P;
  P.x = (const __nv_bfloat16*)d_in[0];
  P.wphi = (const __nv_bfloat16*)d_in[2];
  P.wo = (const __nv_bfloat16*)d_in[3];
  P.logA = (const __nv_bfloat16*)d_in[5];
  P.Aim = (const __nv_bfloat16*)d_in[6];
  P.Cre = (const __nv_bfloat16*)d_in[7];
  P.Cim = (const __nv_bfloat16*)d_in[8];
  P.logdt = (const __nv_bfloat16*)d_in[9];
  P.Dskip = (const __nv_bfloat16*)d_in[10];
  P.out = (__nv_bfloat16*)d_out;
  cudaGetSymbolAddress((void**)&P.xs, g_x);
  P.ts = nullptr;
  cudaFuncSetAttribute(fused_kernel, cudaFuncAttributeMaxDynamicSharedMemorySize, SMEM_BYTES);
  fused_kernel<<<NCTA, NTHREADS, SMEM_BYTES>>>(P, mx, mw, mo, mu, mout, mw4);
}
```

```cpp
#include <cuda_runtime.h>
#include <cuda_bf16.h>
#include <cuda_fp16.h>
#include <cuda.h>
#include <stdint.h>

#define DBG_TS 0

namespace {

constexpr int NTHREADS = 512;
constexpr int NCTA = 128;
constexpr int OFF_W = 0;
constexpr int OFF_X = 98304;
constexpr int OFF_U = OFF_X + 65536;
constexpr int U_CH = 4416, U_ODD = 2240, U_PAD = 128;
constexpr int OFF_STG0 = OFF_U + 18432;
constexpr int SLAB = 3328;
constexpr int OFF_T = OFF_STG0 + 8 * SLAB;
constexpr int T_CH = 5216;
constexpr int T_D = 0;
constexpr int T_5 = 2144;
constexpr int T_3 = T_5 + 384;
constexpr int T_7 = T_5 + 1024;
constexpr int T_9 = T_7 + 320;
constexpr int T_KC = T_9 + 320;
constexpr int T_ST = T_5 - 1024;
constexpr int OFF_PHI = OFF_T + 4 * T_CH;
constexpr int OFF_EYE = OFF_PHI + 1024, OFF_ONE = OFF_EYE + 512;
constexpr int OFF_BAR = OFF_ONE + 256;
constexpr int SMEM_BYTES = OFF_BAR + 512 + 256 * DBG_TS;
constexpr uint32_t SB = 1024;
static_assert(T_KC + 2 * 656 <= T_CH, "table size");
static_assert(SMEM_BYTES <= 232448, "smem");
constexpr int MB_URAW = 0, MB_FULL = 1  , MB_WO = 17, MB_UFULL = 18, MB_OA = 19, MB_OB = 20, MB_OC = 21,
              MB_EMPTY = 22  , MB_AUX = 38;
__host__ __device__ constexpr uint32_t BAR(int i) { return SB + OFF_BAR + 8 * i; }
constexpr int NB_WG0 = 1, NB_ODONE = 2, NB_ST0 = 3  , NB_KV = 5, NB_YZ = 6, NB_INIT = 7, NB_PREP = 8, NB_PROD = 9, NB_KREAD = 10, NB_BDONE = 11;
#define X2_AT -1
#define U_AT 2
#define ZERO_STEP 12
constexpr int SPIN_MAX = 1 << 16;

constexpr int X_CNT = 0;
constexpr int X_PART = 256;
constexpr int X_O = X_PART + 16 * 8 * 144;
constexpr int X_Y = X_O + 32 * 32 * 128;
constexpr int X_UT = X_Y + 512 * 8 * 32;
constexpr int X_SIZE = X_UT + 512 * (U_CH / 16);
__device__ __align__(128) uint4 g_x[X_SIZE];
extern __shared__ uint8_t smem_raw[];
#define TS(i) do {} while (0)
#define TS1(i) do {} while (0)
#define GT(i) do {} while (0)
#define TSDUMP(base) do {} while (0)

__device__ __forceinline__ uint32_t smem_u32(const void* p) { return (uint32_t)__cvta_generic_to_shared(p); }
__device__ __forceinline__ void mbar_arrive(uint32_t b) {
  asm volatile("mbarrier.arrive.shared::cta.b64 _, [%0];" ::"r"(b) : "memory");
}
__device__ __forceinline__ void mbar_wait(uint32_t b) {
  uint32_t done = 0;
#pragma unroll 1
  for (int i = 0; i < SPIN_MAX && !done; i++) {
    asm volatile("{\n.reg .pred p;\nmbarrier.try_wait.parity.shared::cta.b64 p, [%1], 0, 4000;\nselp.u32 %0, 1, 0, p;\n}\n"
                 : "=r"(done) : "r"(b) : "memory");
  }
}
__device__ __forceinline__ void mbar_spin(uint32_t b) {
  uint32_t done = 0;
#pragma unroll 1
  for (int i = 0; i < (SPIN_MAX << 4) && !done; i++) {
    asm volatile("{\n.reg .pred p;\nmbarrier.try_wait.parity.shared::cta.b64 p, [%1], 0;\nselp.u32 %0, 1, 0, p;\n}\n"
                 : "=r"(done) : "r"(b) : "memory");
  }
}
__device__ __forceinline__ void mbar_init(uint32_t b, int n) {
  asm volatile("mbarrier.init.shared::cta.b64 [%0], %1;" ::"r"(b), "r"(n) : "memory");
}
__device__ __forceinline__ void mbar_expect(uint32_t b, int bytes) {
  asm volatile("mbarrier.arrive.expect_tx.shared::cta.b64 _, [%0], %1;" ::"r"(b), "r"(bytes) : "memory");
}
__device__ __forceinline__ void nb_sync(int id, int n) { asm volatile("bar.sync %0, %1;" ::"r"(id), "r"(n) : "memory"); }
__device__ __forceinline__ void nb_arrive(int id, int n) { asm volatile("bar.arrive %0, %1;" ::"r"(id), "r"(n) : "memory"); }
#define ELECT "{\n.reg .pred p;\nelect.sync _|p, 0xffffffff;\n@p "
__device__ __forceinline__ void e_arrive(uint32_t b) {
  asm volatile(ELECT "mbarrier.arrive.shared::cta.b64 _, [%0];\n}\n" ::"r"(b) : "memory");
}
__device__ __forceinline__ void e_expect(uint32_t b, int bytes) {
  asm volatile(ELECT "mbarrier.arrive.expect_tx.shared::cta.b64 _, [%0], %1;\n}\n" ::"r"(b), "r"(bytes) : "memory");
}
__device__ __forceinline__ void e_tma2d(uint32_t dst, const CUtensorMap* m, uint32_t bar, int c0, int c1) {
  asm volatile(ELECT "cp.async.bulk.tensor.2d.shared::cluster.global.mbarrier::complete_tx::bytes [%0], [%1, {%3,%4}], [%2];\n}\n"
               ::"r"(dst), "l"(m), "r"(bar), "r"(c0), "r"(c1) : "memory");
}
__device__ __forceinline__ void e_tma3d(uint32_t dst, const CUtensorMap* m, uint32_t bar, int c0, int c1, int c2) {
  asm volatile(ELECT "cp.async.bulk.tensor.3d.shared::cluster.global.mbarrier::complete_tx::bytes [%0], [%1, {%3,%4,%5}], [%2];\n}\n"
               ::"r"(dst), "l"(m), "r"(bar), "r"(c0), "r"(c1), "r"(c2) : "memory");
}
__device__ __forceinline__ void e_tma4d(uint32_t dst, const CUtensorMap* m, uint32_t bar, int c0, int c3) {
  asm volatile(ELECT "cp.async.bulk.tensor.4d.shared::cluster.global.mbarrier::complete_tx::bytes [%0], [%1, {%3,%5,%5,%4}], [%2];\n}\n"
               ::"r"(dst), "l"(m), "r"(bar), "r"(c0), "r"(c3), "r"(0) : "memory");
}
__device__ __forceinline__ void e_bulk(uint32_t dst, const void* src, int bytes, uint32_t bar) {
  asm volatile(ELECT "cp.async.bulk.shared::cluster.global.mbarrier::complete_tx::bytes [%0], [%1], %2, [%3];\n}\n"
               ::"r"(dst), "l"(src), "r"(bytes), "r"(bar) : "memory");
}
__device__ __forceinline__ void e_prefetch(const void* p, int bytes) {
  asm volatile(ELECT "cp.async.bulk.prefetch.L2.global [%0], %1;\n}\n" ::"l"(p), "r"(bytes) : "memory");
}
__device__ __forceinline__ void e_store2d(const CUtensorMap* m, uint32_t src, int c0, int c1) {
  asm volatile(ELECT "cp.async.bulk.tensor.2d.global.shared::cta.bulk_group [%0, {%2,%3}], [%1];\n}\n"
               ::"l"(m), "r"(src), "r"(c0), "r"(c1) : "memory");
}
__host__ __device__ constexpr uint64_t mkdesc(uint32_t addr, uint32_t lbo, uint32_t sbo, int swz) {
  return (uint64_t)((addr & 0x3FFFF) >> 4) | ((uint64_t)(lbo >> 4) << 16) | ((uint64_t)(sbo >> 4) << 32) |
         ((uint64_t)swz << 62);
}
#define SPLIT() asm volatile("{\n.reg .pred p;\nsetp.eq.u32 p, %0, %1;\n@p exit;\n}\n" ::"r"(blockIdx.y), "n"(__LINE__) : "memory")
#define WG_FENCE() asm volatile("wgmma.fence.sync.aligned;" ::: "memory")
#define WG_COMMIT() asm volatile("wgmma.commit_group.sync.aligned;" ::: "memory")
#define WG_WAIT(n) asm volatile("wgmma.wait_group.sync.aligned " #n ";" ::: "memory")

__device__ __forceinline__ void mma(float& d0, float& d1, float& d2, float& d3, uint32_t a0, uint32_t a1, uint32_t a2,
                                    uint32_t a3, uint32_t b0, uint32_t b1) {
  asm volatile("mma.sync.aligned.m16n8k16.row.col.f32.bf16.bf16.f32 {%0,%1,%2,%3},{%4,%5,%6,%7},{%8,%9},{%0,%1,%2,%3};"
               : "+f"(d0), "+f"(d1), "+f"(d2), "+f"(d3)
               : "r"(a0), "r"(a1), "r"(a2), "r"(a3), "r"(b0), "r"(b1));
}
__device__ __forceinline__ void mmac(float (&d)[4], uint32_t a0, uint32_t a1, uint32_t a2, uint32_t a3, uint32_t b0,
                                     uint32_t b1, const float (&c)[4]) {
  asm volatile("mma.sync.aligned.m16n8k16.row.col.f32.bf16.bf16.f32 {%0,%1,%2,%3},{%4,%5,%6,%7},{%8,%9},{%10,%11,%12,%13};"
               : "=f"(d[0]), "=f"(d[1]), "=f"(d[2]), "=f"(d[3])
               : "r"(a0), "r"(a1), "r"(a2), "r"(a3), "r"(b0), "r"(b1), "f"(c[0]), "f"(c[1]), "f"(c[2]), "f"(c[3]));
}
__device__ __forceinline__ void mma_p(int p, float (&d)[4], uint32_t a0, uint32_t a1, uint32_t a2, uint32_t a3, uint32_t b0, uint32_t b1) {
  asm volatile("{\n.reg .pred q;\nsetp.ne.b32 q, %10, 0;\n"
               "@q mma.sync.aligned.m16n8k16.row.col.f32.bf16.bf16.f32 {%0,%1,%2,%3},{%4,%5,%6,%7},{%8,%9},{%0,%1,%2,%3};\n}\n"
               : "+f"(d[0]), "+f"(d[1]), "+f"(d[2]), "+f"(d[3])
               : "r"(a0), "r"(a1), "r"(a2), "r"(a3), "r"(b0), "r"(b1), "r"(p));
}
__device__ __forceinline__ void mmac_p(int p, float (&d)[4], uint32_t a0, uint32_t a1, uint32_t a2, uint32_t a3, uint32_t b0,
                                       uint32_t b1, const float (&c)[4]) {
  asm volatile("{\n.reg .pred q;\nsetp.ne.b32 q, %14, 0;\n"
               "@q mma.sync.aligned.m16n8k16.row.col.f32.bf16.bf16.f32 {%0,%1,%2,%3},{%4,%5,%6,%7},{%8,%9},{%10,%11,%12,%13};\n}\n"
               : "+f"(d[0]), "+f"(d[1]), "+f"(d[2]), "+f"(d[3])
               : "r"(a0), "r"(a1), "r"(a2), "r"(a3), "r"(b0), "r"(b1), "f"(c[0]), "f"(c[1]), "f"(c[2]), "f"(c[3]), "r"(p));
}
__device__ __forceinline__ void mma_h(float (&d)[4], const uint32_t (&a)[4], uint32_t b0, uint32_t b1) {
  asm volatile("mma.sync.aligned.m16n8k16.row.col.f32.f16.f16.f32 {%0,%1,%2,%3},{%4,%5,%6,%7},{%8,%9},{%0,%1,%2,%3};"
               : "+f"(d[0]), "+f"(d[1]), "+f"(d[2]), "+f"(d[3]) : "r"(a[0]), "r"(a[1]), "r"(a[2]), "r"(a[3]), "r"(b0), "r"(b1));
}
__device__ __forceinline__ void mma0(float& d0, float& d1, float& d2, float& d3, uint32_t a0, uint32_t a1, uint32_t a2,
                                     uint32_t a3, uint32_t b0, uint32_t b1) {
  asm volatile("mma.sync.aligned.m16n8k16.row.col.f32.bf16.bf16.f32 {%0,%1,%2,%3},{%4,%5,%6,%7},{%8,%9},{%10,%10,%10,%10};"
               : "=f"(d0), "=f"(d1), "=f"(d2), "=f"(d3)
               : "r"(a0), "r"(a1), "r"(a2), "r"(a3), "r"(b0), "r"(b1), "f"(0.f));
}
__device__ __forceinline__ uint32_t pack_bf(float lo, float hi) {
  uint32_t r;
  asm("cvt.rn.bf16x2.f32 %0, %1, %2;" : "=r"(r) : "f"(hi), "f"(lo));
  return r;
}
__device__ __forceinline__ float bf_lo(uint32_t w) { return __uint_as_float(w << 16); }
__device__ __forceinline__ float bf_hi(uint32_t w) { return __uint_as_float(w & 0xffff0000u); }
__device__ __forceinline__ float bf_round(float x) { return __bfloat162float(__float2bfloat16_rn(x)); }
__device__ __forceinline__ uint32_t bmax2(uint32_t a, uint32_t b) {
  uint32_t r; asm("max.bf16x2 %0, %1, %2;" : "=r"(r) : "r"(a), "r"(b)); return r;
}
__device__ __forceinline__ uint32_t bmin2(uint32_t a, uint32_t b) {
  uint32_t r; asm("min.bf16x2 %0, %1, %2;" : "=r"(r) : "r"(a), "r"(b)); return r;
}
__device__ __forceinline__ float ex2(float x) { float r; asm("ex2.approx.ftz.f32 %0, %1;" : "=f"(r) : "f"(x)); return r; }
__device__ __forceinline__ float rcp(float x) { float r; asm("rcp.approx.ftz.f32 %0, %1;" : "=f"(r) : "f"(x)); return r; }
__device__ __forceinline__ void ldsm4(uint32_t (&r)[4], uint32_t a) {
  asm volatile("ldmatrix.sync.aligned.m8n8.x4.shared.b16 {%0,%1,%2,%3}, [%4];"
               : "=r"(r[0]), "=r"(r[1]), "=r"(r[2]), "=r"(r[3]) : "r"(a) : "memory");
}
__device__ __forceinline__ void ldsm4t(uint32_t (&r)[4], uint32_t a) {
  asm volatile("ldmatrix.sync.aligned.m8n8.x4.trans.shared.b16 {%0,%1,%2,%3}, [%4];"
               : "=r"(r[0]), "=r"(r[1]), "=r"(r[2]), "=r"(r[3]) : "r"(a) : "memory");
}
__device__ __forceinline__ void stsm4(uint32_t a, uint32_t r0, uint32_t r1, uint32_t r2, uint32_t r3) {
  asm volatile("stmatrix.sync.aligned.m8n8.x4.shared.b16 [%0], {%1,%2,%3,%4};"
               ::"r"(a), "r"(r0), "r"(r1), "r"(r2), "r"(r3) : "memory");
}
__device__ __forceinline__ uint32_t lds32(uint32_t a) {
  uint32_t r; asm volatile("ld.shared.u32 %0, [%1];" : "=r"(r) : "r"(a) : "memory"); return r;
}
__device__ __forceinline__ uint32_t lds16(uint32_t a) {
  uint32_t r; asm volatile("{\n.reg .u16 h;\nld.shared.u16 h, [%1];\ncvt.u32.u16 %0, h;\n}\n" : "=r"(r) : "r"(a) : "memory"); return r;
}
__device__ __forceinline__ uint2 lds64(uint32_t a) {
  uint2 r; asm volatile("ld.shared.v2.u32 {%0,%1}, [%2];" : "=r"(r.x), "=r"(r.y) : "r"(a) : "memory"); return r;
}
__device__ __forceinline__ uint4 lds128(uint32_t a) {
  uint4 r;
  asm volatile("ld.shared.v4.u32 {%0,%1,%2,%3}, [%4];" : "=r"(r.x), "=r"(r.y), "=r"(r.z), "=r"(r.w) : "r"(a) : "memory");
  return r;
}
__device__ __forceinline__ void sts32(uint32_t a, uint32_t v) { asm volatile("st.shared.u32 [%0], %1;" ::"r"(a), "r"(v) : "memory"); }
__device__ __forceinline__ void sts16(uint32_t a, uint32_t v) {
  asm volatile("{\n.reg .u16 h;\ncvt.u16.u32 h, %1;\nst.shared.u16 [%0], h;\n}\n" ::"r"(a), "r"(v) : "memory");
}
__device__ __forceinline__ void sts64(uint32_t a, uint32_t x, uint32_t y) {
  asm volatile("st.shared.v2.u32 [%0], {%1,%2};" ::"r"(a), "r"(x), "r"(y) : "memory");
}
__device__ __forceinline__ void sts128(uint32_t a, uint32_t x, uint32_t y, uint32_t z, uint32_t w) {
  asm volatile("st.shared.v4.u32 [%0], {%1,%2,%3,%4};" ::"r"(a), "r"(x), "r"(y), "r"(z), "r"(w) : "memory");
}
__device__ __forceinline__ uint4 ld_x(const uint4* p) {
  uint4 r;
  asm volatile("{\n.reg .b128 t;\nld.relaxed.gpu.global.b128 t, [%4];\nmov.b128 {%0,%1,%2,%3}, t;\n}\n"
               : "=r"(r.x), "=r"(r.y), "=r"(r.z), "=r"(r.w) : "l"(p) : "memory");
  return r;
}
__device__ __forceinline__ uint32_t ld_x32(const uint32_t* p) {
  uint32_t r; asm volatile("ld.relaxed.gpu.global.u32 %0, [%1];" : "=r"(r) : "l"(p) : "memory"); return r;
}
__device__ __forceinline__ void st_x(uint4* p, uint32_t x, uint32_t y, uint32_t z, uint32_t w) {
  asm volatile("{\n.reg .b128 t;\nmov.b128 t, {%1,%2,%3,%4};\nst.relaxed.gpu.global.b128 [%0], t;\n}\n"
               ::"l"(p), "r"(x), "r"(y), "r"(z), "r"(w) : "memory");
}
__device__ __forceinline__ void st_x_p(int p, uint4* a, uint32_t x, uint32_t y, uint32_t z, uint32_t w) {
  asm volatile("{\n.reg .b128 t;\n.reg .pred q;\nsetp.ne.b32 q, %5, 0;\nmov.b128 t, {%1,%2,%3,%4};\n@q st.relaxed.gpu.global.b128 [%0], t;\n}\n"
               ::"l"(a), "r"(x), "r"(y), "r"(z), "r"(w), "r"(p) : "memory");
}
__device__ __forceinline__ void sts64_p(int p, uint32_t a, uint32_t x, uint32_t y) {
  asm volatile("{\n.reg .pred q;\nsetp.ne.b32 q, %3, 0;\n@q st.shared.v2.u32 [%0], {%1,%2};\n}\n" ::"r"(a), "r"(x), "r"(y), "r"(p) : "memory");
}
__device__ __forceinline__ void st_x32(uint32_t* p, uint32_t x) {
  asm volatile("st.relaxed.gpu.global.u32 [%0], %1;" ::"l"(p), "r"(x) : "memory");
}
__device__ __forceinline__ uint32_t nz(uint32_t w) { return max(w, 1u); }
__device__ __forceinline__ uint32_t fu(float x) { return __float_as_uint(x); }
__device__ __forceinline__ float uf(uint32_t x) { return __uint_as_float(x); }

__device__ __forceinline__ void wgmma_ss_n96(float (&d)[48], uint64_t da, uint64_t db, int sc) {
  asm volatile("{\n.reg .pred p;\nsetp.ne.b32 p, %50, 0;\n"
      "wgmma.mma_async.sync.aligned.m64n96k16.f32.bf16.bf16 "
      "{%0,%1,%2,%3,%4,%5,%6,%7,%8,%9,%10,%11,%12,%13,%14,%15,%16,%17,%18,%19,%20,%21,%22,%23,%24,%25,%26,%27,%28,%29,%30,%31,%32,%33,%34,%35,%36,%37,%38,%39,%40,%41,%42,%43,%44,%45,%46,%47}, "
      "%48, %49, p, 1, 1, 0, 1;\n}\n"
      : "+f"(d[0]), "+f"(d[1]), "+f"(d[2]), "+f"(d[3]), "+f"(d[4]), "+f"(d[5]), "+f"(d[6]), "+f"(d[7]),
        "+f"(d[8]), "+f"(d[9]), "+f"(d[10]), "+f"(d[11]), "+f"(d[12]), "+f"(d[13]), "+f"(d[14]), "+f"(d[15]),
        "+f"(d[16]), "+f"(d[17]), "+f"(d[18]), "+f"(d[19]), "+f"(d[20]), "+f"(d[21]), "+f"(d[22]), "+f"(d[23]),
        "+f"(d[24]), "+f"(d[25]), "+f"(d[26]), "+f"(d[27]), "+f"(d[28]), "+f"(d[29]), "+f"(d[30]), "+f"(d[31]),
        "+f"(d[32]), "+f"(d[33]), "+f"(d[34]), "+f"(d[35]), "+f"(d[36]), "+f"(d[37]), "+f"(d[38]), "+f"(d[39]),
        "+f"(d[40]), "+f"(d[41]), "+f"(d[42]), "+f"(d[43]), "+f"(d[44]), "+f"(d[45]), "+f"(d[46]), "+f"(d[47])
      : "l"(da), "l"(db), "r"(sc));
}

__device__ __forceinline__ void wgmma_ss_n128(float (&d)[64], uint64_t da, uint64_t db, int sc) {
  asm volatile("{\n.reg .pred p;\nsetp.ne.b32 p, %66, 0;\n"
      "wgmma.mma_async.sync.aligned.m64n128k16.f32.bf16.bf16 "
      "{%0,%1,%2,%3,%4,%5,%6,%7,%8,%9,%10,%11,%12,%13,%14,%15,%16,%17,%18,%19,%20,%21,%22,%23,%24,%25,%26,%27,%28,%29,%30,%31,%32,%33,%34,%35,%36,%37,%38,%39,%40,%41,%42,%43,%44,%45,%46,%47,%48,%49,%50,%51,%52,%53,%54,%55,%56,%57,%58,%59,%60,%61,%62,%63}, "
      "%64, %65, p, 1, 1, 0, 1;\n}\n"
      : "+f"(d[0]), "+f"(d[1]), "+f"(d[2]), "+f"(d[3]), "+f"(d[4]), "+f"(d[5]), "+f"(d[6]), "+f"(d[7]),
        "+f"(d[8]), "+f"(d[9]), "+f"(d[10]), "+f"(d[11]), "+f"(d[12]), "+f"(d[13]), "+f"(d[14]), "+f"(d[15]),
        "+f"(d[16]), "+f"(d[17]), "+f"(d[18]), "+f"(d[19]), "+f"(d[20]), "+f"(d[21]), "+f"(d[22]), "+f"(d[23]),
        "+f"(d[24]), "+f"(d[25]), "+f"(d[26]), "+f"(d[27]), "+f"(d[28]), "+f"(d[29]), "+f"(d[30]), "+f"(d[31]),
        "+f"(d[32]), "+f"(d[33]), "+f"(d[34]), "+f"(d[35]), "+f"(d[36]), "+f"(d[37]), "+f"(d[38]), "+f"(d[39]),
        "+f"(d[40]), "+f"(d[41]), "+f"(d[42]), "+f"(d[43]), "+f"(d[44]), "+f"(d[45]), "+f"(d[46]), "+f"(d[47]),
        "+f"(d[48]), "+f"(d[49]), "+f"(d[50]), "+f"(d[51]), "+f"(d[52]), "+f"(d[53]), "+f"(d[54]), "+f"(d[55]),
        "+f"(d[56]), "+f"(d[57]), "+f"(d[58]), "+f"(d[59]), "+f"(d[60]), "+f"(d[61]), "+f"(d[62]), "+f"(d[63])
      : "l"(da), "l"(db), "r"(sc));
}

__device__ __forceinline__ void wgmma_ss_n40(float (&d)[20], uint64_t da, uint64_t db, int sc) {
  asm volatile("{\n.reg .pred p;\nsetp.ne.b32 p, %22, 0;\n"
      "wgmma.mma_async.sync.aligned.m64n40k16.f32.bf16.bf16 "
      "{%0,%1,%2,%3,%4,%5,%6,%7,%8,%9,%10,%11,%12,%13,%14,%15,%16,%17,%18,%19}, "
      "%20, %21, p, 1, 1, 1, 1;\n}\n"
      : "+f"(d[0]), "+f"(d[1]), "+f"(d[2]), "+f"(d[3]), "+f"(d[4]), "+f"(d[5]), "+f"(d[6]), "+f"(d[7]),
        "+f"(d[8]), "+f"(d[9]), "+f"(d[10]), "+f"(d[11]), "+f"(d[12]), "+f"(d[13]), "+f"(d[14]), "+f"(d[15]),
        "+f"(d[16]), "+f"(d[17]), "+f"(d[18]), "+f"(d[19])
      : "l"(da), "l"(db), "r"(sc));
}

__device__ __forceinline__ void wgmma_rs_n8(float (&d)[4], const uint4& a, uint64_t db, int sc) {
  asm volatile("{\n.reg .pred p;\nsetp.ne.b32 p, %9, 0;\n"
      "wgmma.mma_async.sync.aligned.m64n8k16.f32.bf16.bf16 "
      "{%0,%1,%2,%3}, "
      "{%4,%5,%6,%7}, %8, p, 1, 1, 1;\n}\n"
      : "+f"(d[0]), "+f"(d[1]), "+f"(d[2]), "+f"(d[3])
      : "r"(a.x), "r"(a.y), "r"(a.z), "r"(a.w), "l"(db), "r"(sc));
}

__device__ __forceinline__ void wgmma_rs_n16(float (&d)[8], const uint4& a, uint64_t db, int sc) {
  asm volatile("{\n.reg .pred p;\nsetp.ne.b32 p, %13, 0;\n"
      "wgmma.mma_async.sync.aligned.m64n16k16.f32.bf16.bf16 "
      "{%0,%1,%2,%3,%4,%5,%6,%7}, "
      "{%8,%9,%10,%11}, %12, p, 1, 1, 1;\n}\n"
      : "+f"(d[0]), "+f"(d[1]), "+f"(d[2]), "+f"(d[3]), "+f"(d[4]), "+f"(d[5]), "+f"(d[6]), "+f"(d[7])
      : "r"(a.x), "r"(a.y), "r"(a.z), "r"(a.w), "l"(db), "r"(sc));
}

__device__ __forceinline__ void wgmma_rs_n24(float (&d)[12], const uint4& a, uint64_t db, int sc) {
  asm volatile("{\n.reg .pred p;\nsetp.ne.b32 p, %17, 0;\n"
      "wgmma.mma_async.sync.aligned.m64n24k16.f32.bf16.bf16 "
      "{%0,%1,%2,%3,%4,%5,%6,%7,%8,%9,%10,%11}, "
      "{%12,%13,%14,%15}, %16, p, 1, 1, 1;\n}\n"
      : "+f"(d[0]), "+f"(d[1]), "+f"(d[2]), "+f"(d[3]), "+f"(d[4]), "+f"(d[5]), "+f"(d[6]), "+f"(d[7]),
        "+f"(d[8]), "+f"(d[9]), "+f"(d[10]), "+f"(d[11])
      : "r"(a.x), "r"(a.y), "r"(a.z), "r"(a.w), "l"(db), "r"(sc));
}

struct Params {
  const __nv_bfloat16 *logA, *Aim, *Cre, *Cim, *logdt, *Dskip, *x, *wphi, *wo;
  __nv_bfloat16* out;
  uint4* xs;
  long long* ts;
};

__device__ __forceinline__ uint4 tr_row(const uint4 (&v)[8], int i) {
  uint32_t o[4];
#pragma unroll
  for (int m = 0; m < 4; m++) {
    const uint4 &ra = v[2 * m], &rb = v[2 * m + 1];
    const int k = i >> 1;
    const uint32_t xa = k == 0 ? ra.x : k == 1 ? ra.y : k == 2 ? ra.z : ra.w;
    const uint32_t xb = k == 0 ? rb.x : k == 1 ? rb.y : k == 2 ? rb.z : rb.w;
    o[m] = __byte_perm(xa, xb, (i & 1) ? 0x7632 : 0x5410);
  }
  return make_uint4(o[0], o[1], o[2], o[3]);
}

struct cpx { float r, i; };
__device__ __forceinline__ cpx csq(cpx a) { return {a.r * a.r - a.i * a.i, 2.f * (a.r * a.i)}; }
__device__ __forceinline__ cpx polar(float e, float t) {
  const float m = ex2(e);
  return {m * __cosf(t), m * __sinf(t)};
}

struct KgenRaw { unsigned short la, ai, cr, ci, ldt; };
__device__ __forceinline__ KgenRaw kgen_load(const Params& P, int d, int unit, int lane) {
  const int o = d * 128 + unit * 32 + lane;
  return {__ldg((const unsigned short*)P.logA + o), __ldg((const unsigned short*)P.Aim + o), __ldg((const unsigned short*)P.Cre + o),
          __ldg((const unsigned short*)P.Cim + o), __ldg((const unsigned short*)P.logdt + d)};
}
struct hmul { __half2 a, b; };
__device__ __forceinline__ hmul mk_mul(cpx w) {
  uint32_t b;
  asm("{\n.reg .f32 n;\nneg.ftz.f32 n, %1;\ncvt.rn.f16x2.f32 %0, %2, n;\n}\n" : "=r"(b) : "f"(w.i), "f"(w.r));
  return {__floats2half2_rn(w.r, w.i), *(const __half2*)&b};
}
__device__ __forceinline__ __half2 hcm(__half2 z, const hmul& w) { return __hfma2(__high2half2(z), w.b, __hmul2(__low2half2(z), w.a)); }
__device__ __forceinline__ uint32_t hu(__half2 v) { return *(const uint32_t*)&v; }

struct KgenAddr { uint32_t sa, sb, lb, lc, la; };
__device__ __forceinline__ KgenAddr kgen_addr(int lane, uint32_t buf) {
  KgenAddr a;
  a.sa = buf + (lane & 7) * 128 + ((((lane >> 3) ^ lane) & 7) << 4);
  a.lb = buf + (lane >> 3) * 128 + (((lane ^ (lane >> 3)) & 7) << 4);
  a.la = buf + ((lane >> 3) & 1) * 1024 + (lane >> 4) * 128 + (((lane ^ (lane >> 4)) & 7) << 4);
  a.sb = a.sa ^ 64; a.lc = a.lb ^ 64;
  asm volatile("" : "+r"(a.sa), "+r"(a.sb), "+r"(a.lb), "+r"(a.lc), "+r"(a.la));
  return a;
}
__device__ __forceinline__ void kgen_unit(const KgenRaw& r, const KgenAddr& ad, uint32_t zero, float (&k)[5][4], float& k2048, float& sc) {
  const float dt = bf_round(expf(bf_lo(r.ldt)));
  const float a2 = bf_round(ex2(bf_lo(r.la) * 1.4426950408889634f)) * (dt * -1.4426950408889634f);
  const float f = bf_lo(r.ai) * dt;
  const float r128 = f * 20.371832715762604f;
  const uint32_t ex = min(max(__reduce_max_sync(0xffffffffu, max(r.cr & 0x7fffu, r.ci & 0x7fffu)) >> 7, 1u), 253u);
  const float cs = uf((254u - ex) << 23);
  sc = 2.f * dt * uf(ex << 23);
  const cpx C = {bf_lo(r.cr) * cs, -bf_lo(r.ci) * cs};
  auto put = [&](const __half2 (&v)[8], uint32_t off) {
    stsm4(ad.sa + off, hu(v[0]), hu(v[1]), hu(v[2]), hu(v[3]));
    stsm4(ad.sb + off, hu(v[4]), hu(v[5]), hu(v[6]), hu(v[7]));
  };
  uint32_t A[4][4], B[5][2][4];
  auto get = [&](int j, uint32_t off) {
    __syncwarp();
    ldsm4(B[j][0], ad.lb + off);
    ldsm4(B[j][1], ad.lc + 512 + off);
  };
  auto tile = [&](int j) {
    k[j][0] = k[j][1] = k[j][2] = k[j][3] = 0.f;
#pragma unroll
    for (int s = 0; s < 4; s++) mma_h(k[j], A[s], B[j][s >> 1][2 * (s & 1)], B[j][s >> 1][2 * (s & 1) + 1]);
  };
  auto after = [&](cpx v, uint32_t dep) { return cpx{uf(fu(v.r) ^ (dep & zero)), v.i}; };
  const cpx w1 = polar(a2, f), w128 = polar(a2 * 128.f, (r128 - rintf(r128)) * 6.283185307179586f);
  const cpx w2 = csq(w1), w4 = csq(w2);
  __half2 t0[8], t1[8], t2[8], t3[8], t4[8];
  const hmul m2 = mk_mul(w2), m4 = mk_mul(w4), m128 = mk_mul(w128);
  t0[0] = __floats2half2_rn(1.f, 0.f); t0[1] = __floats2half2_rn(w1.r, w1.i); t0[2] = m2.a; t0[4] = m4.a;
  t0[3] = hcm(t0[1], m2); t0[5] = hcm(t0[1], m4); t0[6] = hcm(t0[2], m4); t0[7] = hcm(t0[3], m4);
  put(t0, 0); get(0, 0);
  t1[0] = m128.a;
#pragma unroll
  for (int i = 1; i < 8; i++) t1[i] = hcm(t0[i], m128);
  put(t1, 1024); get(1, 1024);
  {
    cpx w8 = csq(after(w4, B[0][0][0]));
    w8.i = -w8.i;
    const cpx w16 = csq(w8), w32 = csq(w16), w64 = csq(w32);
    const hmul m8 = mk_mul(w8), m16 = mk_mul(w16), m32 = mk_mul(w32), m64 = mk_mul(w64);
    __half2 a[8];
    a[0] = __floats2half2_rn(C.r, C.i); a[1] = hcm(a[0], m8);
    a[2] = hcm(a[0], m16); a[3] = hcm(a[1], m16);
#pragma unroll
    for (int i = 0; i < 4; i++) a[4 + i] = hcm(a[i], m32);
    put(a, 0);
#pragma unroll
    for (int i = 0; i < 8; i++) a[i] = hcm(a[i], m64);
    put(a, 1024);
    __syncwarp();
#pragma unroll
    for (int s = 0; s < 4; s++) ldsm4(A[s], (ad.la ^ (s << 5)) + s * 256);
  }
  const cpx w256 = csq(after(w128, B[1][0][0]));
  const hmul m256 = mk_mul(w256);
  t2[0] = m256.a;
#pragma unroll
  for (int i = 1; i < 8; i++) t2[i] = hcm((i & 1) ? t1[i & 6] : t0[i & 6], m256);
  put(t2, 0); get(2, 0);
  tile(0); tile(1);
  const cpx w512 = csq(after(w256, A[0][0]));
  const hmul m512 = mk_mul(w512);
  t3[0] = m512.a;
#pragma unroll
  for (int i = 1; i < 8; i++) t3[i] = hcm((i & 2) ? t2[i & 5] : ((i & 1) ? t1[i & 4] : t0[i & 4]), m512);
  put(t3, 1024); get(3, 1024);
  tile(2);
  const cpx w1024 = csq(after(w512, B[2][0][0])), we = csq(w1024);
  const hmul m1024 = mk_mul(w1024);
  t4[0] = m1024.a;
#pragma unroll
  for (int i = 1; i < 8; i++) t4[i] = hcm((i & 4) ? t3[i & 3] : ((i & 2) ? t2[i & 1] : t1[0]), m1024);
  put(t4, 0); get(4, 0);
  tile(3); tile(4);
  k2048 = (C.r * we.r + C.i * we.i) * sc;
}

__device__ __forceinline__ void build_tables(uint32_t tb, int lane, float (&k)[5][4], float k2048) {
  const int g = lane >> 2, c = lane & 3;
  const uint32_t kc = tb + T_KC + 16;
  {
    const uint32_t a0 = kc + 16 * g + 4 * c, a2 = kc + 2 * (256 + 4 * g + c);
    const uint32_t a3 = kc + 2 * (384 + 2 * g + 64 * (c & 1) + (c >> 1)), a4 = kc + 2 * (512 + g + 32 * c);
#pragma unroll
    for (int r = 0; r < 2; r++) {
      sts32(a0 + 128 * r, pack_bf(k[0][2 * r], k[0][2 * r + 1]));
      sts32(a0 + 128 * r + 256, pack_bf(k[1][2 * r], k[1][2 * r + 1]));
      const uint32_t w2 = pack_bf(k[2][2 * r], k[2][2 * r + 1]);
      const uint32_t w3 = pack_bf(k[3][2 * r], k[3][2 * r + 1]);
      const uint32_t w4 = pack_bf(k[4][2 * r], k[4][2 * r + 1]);
      sts16(a2 + 64 * r, w2); sts16(a2 + 64 * r + 128, w2 >> 16);
      sts16(a3 + 32 * r, w3); sts16(a3 + 32 * r + 64, w3 >> 16);
      sts16(a4 + 16 * r, w4); sts16(a4 + 16 * r + 32, w4 >> 16);
    }
  }
  if (lane == 0) { sts16(kc + 2 * 640, pack_bf(k2048, 0.f)); sts32(kc - 4, 0); }
  __syncwarp();
  const uint32_t td = tb + T_D + 32;
#pragma unroll
  for (int hf = 0; hf < 2; hf++) {
    const uint2 v = lds64(kc + 256 * hf + 8 * lane);
    const uint32_t pv = lds32(kc + 256 * hf + 8 * lane - 4);
    sts128(td + 512 * hf + 16 * lane, __byte_perm(v.x, pv, 0x7610), __byte_perm(v.x, v.x, 0x1032), __byte_perm(v.y, v.x, 0x7610),
           __byte_perm(v.y, v.y, 0x1032));
  }
#pragma unroll
  for (int hf = 0; hf < 2; hf++) {
    const uint32_t v = lds32(kc + 512 + 128 * hf + 4 * lane), nx = lds32(kc + 516 + 128 * hf + 4 * lane);
    uint32_t w0 = __byte_perm(v, v, 0x1010);
    const uint32_t w1 = w0;
    if (hf == 0) { const uint32_t pv = lds32(kc + 508); if (lane == 0) w0 = __byte_perm(v, pv, 0x7610); }
    sts128(td + 1024 + 512 * hf + 16 * lane, w0, w1, __byte_perm(v, v, 0x1032), __byte_perm(nx, v, 0x7610));
  }
  {
    const uint32_t kk = lds16(kc + 2 * 384);
    const uint32_t w = lane < 3 ? (kk | (kk << 16)) : (lane == 3 ? (kk << 16) : 0u);
    if (lane < 24) sts32(td + 4 * (lane < 16 ? 512 + lane : lane - 24), w);
    const uint32_t lo_ = lds16(kc + 2 * 511), le_ = lds16(kc + 2 * 512);
    const uint32_t ja = tb + T_5 + (lane < 16 ? 4 * lane : 256 + 4 * lane);
    sts32(ja, lane == 16 ? (le_ << 16) : 0u);
    sts32(ja + 384, lane == 16 ? (lo_ << 16) : 0u);
    sts32(tb + (lane < 16 ? T_7 : T_9 - 64) + 4 * lane, 0u);
  }
#pragma unroll
  for (int s = 0; s < 2; s++) {
    const uint32_t b = kc + 2 * (s ? 512 : 384) + 8 * lane;
    const uint2 v = lds64(b);
    uint32_t em = lds16(b - 2), e0 = v.x;
    const uint32_t e4 = lds16(b + 8);
    if (lane == 0) { em = 0; e0 = 0; }
    sts64(tb + (s ? T_7 : T_3) + 64 + 8 * lane, __byte_perm(v.x, em, 0x5432), __byte_perm(v.y, v.x, 0x7632));
    sts64(tb + (s ? T_9 : T_5) + 64 + 8 * lane, __byte_perm(v.y, e0, 0x5410), __byte_perm(e4, v.y, 0x5410));
  }
  __syncwarp();
}

__device__ __forceinline__ uint32_t box2w(int lo, int n, int o) {
  return ((unsigned)(o - lo) < (unsigned)n ? 0x3F80u : 0u) | ((unsigned)(o + 1 - lo) < (unsigned)n ? 0x3F800000u : 0u);
}

__device__ __forceinline__ void conv_channel(uint32_t ub, uint32_t tb, int lane, uint4* ydst) {
  const int g = lane >> 2, c = lane & 3, x = g - 2 * c;
  const int mi = lane >> 3;
  const uint32_t qa = ub + U_PAD + 16 * (lane & 7) + ((mi == 0 || mi == 3) ? U_ODD : 0) - (mi == 0 ? 16 : 0);
  const uint32_t hb = ub + U_PAD + (mi & 1) * U_ODD + 16 * ((lane >> 4) + (lane & 7)) - 16;
  const uint32_t kv = lds16(tb + T_KC + 16 + 2 * 512);
  const int oh = c < 2 ? 8 + 2 * c : 2 * c - 8, og = c < 3 ? 2 * c : -10;
  uint32_t bx[4] = {box2w(g - 4, 9, 2 * c), box2w(g - 3, 7, 2 * c), box2w(g - 4, 9, oh), box2w(g - 3, 7, oh)};
  uint32_t by[4] = {box2w(g - 10, 5, 2 * c - 8), box2w(g - 5, 3, 2 * c - 8), box2w(g - 10, 5, og), box2w(g - 5, 3, og)};
  uint32_t lb0 = ((unsigned)(x + 5) < 2u ? kv : 0u) | ((unsigned)(x + 4) < 2u ? kv << 16 : 0u);
  uint32_t lb1 = ((unsigned)(x - 3) < 2u ? kv : 0u) | ((unsigned)(x - 4) < 2u ? kv << 16 : 0u);
  const int q0 = g - 1, q1 = c < 3 ? g : g - 2;
  uint32_t y0a = ub + U_PAD + (q0 & 1) * U_ODD + 16 * (q0 >> 1) + 4 * c;
  uint32_t y1a = ub + U_PAD + (q1 & 1) * U_ODD + 16 * (q1 >> 1) + 4 * c;
#pragma unroll
  for (int i = 0; i < 4; i++) asm volatile("" : "+r"(bx[i]), "+r"(by[i]));
  asm volatile("" : "+r"(lb0), "+r"(lb1), "+r"(y0a), "+r"(y1a));
  mbar_wait(BAR(MB_UFULL));
  mbar_spin(BAR(MB_EMPTY + 15));
  TS(36);
  float acc[16][4];
  {
    uint32_t z09[8], z07[8], zm9[8], zm7[8];
#pragma unroll
    for (int i = 0; i < 8; i++) {
      uint32_t h[4];
      ldsm4(h, hb + 128 * i);
      float y0, y1, y2, y3, w0, w1, w2, w3;
      mma0(y0, y1, y2, y3, bx[0], bx[1], bx[2], bx[3], h[2], c < 2 ? h[3] : h[1]);
      mma0(w0, w1, w2, w3, bx[0], bx[1], bx[2], bx[3], h[1], c < 2 ? h[2] : h[0]);
      z09[i] = pack_bf(y0, y1); z07[i] = pack_bf(y2, y3);
      zm9[i] = pack_bf(w0, w1); zm7[i] = pack_bf(w2, w3);
    }
  uint32_t f3[3][4][4];
  {
    const uint32_t fa = tb + T_7 + 4 * (16 + x);
#pragma unroll
    for (int tt = 0; tt < 3; tt++)
#pragma unroll
      for (int D = 0; D < 4; D++) {
        const uint32_t a = fa + (tt == 0 ? 316 : (tt == 1 ? 320 : 0)) + 64 * D;
        f3[tt][D][0] = lds32(a); f3[tt][D][1] = lds32(a + 32); f3[tt][D][2] = lds32(a - 32); f3[tt][D][3] = lds32(a);
      }
  }
    float a[4][2][4];
#pragma unroll
    for (int kap = 0; kap < 4; kap++)
#pragma unroll
      for (int sg = 0; sg < 2; sg++)
#pragma unroll
        for (int bk = 3; bk >= kap; bk--) {
          const uint32_t(&q0_)[4] = f3[sg ? 2 : 0][bk - kap];
          const uint32_t(&q1_)[4] = f3[sg ? 2 : 1][bk - kap];
          float(&a0)[4] = a[bk][0];
          float(&a1)[4] = a[bk][1];
          if (sg == 0 && kap == 0) {
            mma0(a0[0], a0[1], a0[2], a0[3], q0_[0], q0_[1], q0_[2], q0_[3], z09[0], z09[1]);
            mma0(a1[0], a1[1], a1[2], a1[3], q1_[0], q1_[1], q1_[2], q1_[3], zm9[0], zm9[1]);
          } else {
            mma(a0[0], a0[1], a0[2], a0[3], q0_[0], q0_[1], q0_[2], q0_[3], sg ? zm7[2 * kap] : z09[2 * kap], sg ? zm7[2 * kap + 1] : z09[2 * kap + 1]);
            mma(a1[0], a1[1], a1[2], a1[3], q1_[0], q1_[1], q1_[2], q1_[3], sg ? z07[2 * kap] : zm9[2 * kap], sg ? z07[2 * kap + 1] : zm9[2 * kap + 1]);
          }
        }
    SPLIT();
#pragma unroll
    for (int i = 0; i < 8; i++) {
      uint32_t h[4];
      ldsm4(h, qa + 128 * i);
      const float ci[4] = {a[i >> 1][0][2 * (i & 1)], a[i >> 1][0][2 * (i & 1) + 1], a[i >> 1][1][2 * (i & 1)], a[i >> 1][1][2 * (i & 1) + 1]};
      mmac(acc[8 + i], h[0], h[1], h[2], h[3], lb0, lb1, ci);
    }
  }
  TS(44);
  {
    uint2 a5[10], a3[10];
    const uint32_t aa = tb + T_5 + 4 * (8 + 2 * g - 2 * c);
#pragma unroll
    for (int m = 0; m < 10; m++) { a5[m] = lds64(aa + 32 * m); a3[m] = lds64(aa + 384 + 32 * m); }
    uint32_t x5[12][2], x3[12][2];
    auto ygen = [&](int kap) {
#pragma unroll
      for (int hh = 0; hh < 2; hh++) {
        float y0, y1, y2, y3;
        mma0(y0, y1, y2, y3, by[0], by[1], by[2], by[3], lds32(y0a + 128 * kap + 64 * hh), lds32(y1a + 128 * kap + 64 * hh));
        x5[kap][hh] = pack_bf(y0, y1);
        x3[kap][hh] = pack_bf(y2, y3);
      }
    };
    ygen(11); ygen(10); ygen(9); ygen(8);
#pragma unroll
    for (int kap = 11; kap >= 0; kap--) {
      if (kap >= 4) ygen(kap - 4);
#pragma unroll
      for (int sg = 0; sg < 2; sg++)
#pragma unroll
        for (int i = 4; i >= 0; i--) {
          const int be = kap + 4 + i;
          if (be <= 15) {
            const uint2 &hi = sg ? a3[2 * i + 1] : a5[2 * i + 1], &lo = sg ? a3[2 * i] : a5[2 * i];
            const uint32_t b0 = sg ? x3[kap][0] : x5[kap][0], b1 = sg ? x3[kap][1] : x5[kap][1];
            if (be < 8 && i == 0 && sg == 0) mma0(acc[be][0], acc[be][1], acc[be][2], acc[be][3], hi.x, hi.y, lo.x, lo.y, b0, b1);
            else mma(acc[be][0], acc[be][1], acc[be][2], acc[be][3], hi.x, hi.y, lo.x, lo.y, b0, b1);
          }
        }
    }
  }
  TS(45);
  {
    const uint32_t st = tb + T_ST + lane * 8;
#pragma unroll
    for (int be = 4; be < 12; be++) sts64(st + 256 * be, pack_bf(acc[be][0], acc[be][1]), pack_bf(acc[be][2], acc[be][3]));
    SPLIT();
    uint32_t F[66], qd[8][4];
    const uint32_t fa = tb + T_D + 32 + 4 * x;
#pragma unroll
    for (int i = 0; i < 32; i++) {
      const int s = 120 - (i >> 2) - 8 * (i & 3);
      uint32_t(&q)[4] = qd[i & 7];
      ldsm4(q, qa + 16 * s);
      const int m = 16 * (i & 3) + 2 * (i >> 2);
      F[m] = lds32(fa + 32 * m); F[m + 1] = lds32(fa + 32 * m + 32);
#pragma unroll
      for (int be = 15; be >= 12; be--) {
        const int de = 8 * be - s;
        float(&a)[4] = (be >= 14 && !(i & 1)) ? acc[be - 4] : acc[be];
        if (de >= 0 && be >= 14 && i == 2 * (15 - be)) mma0(a[0], a[1], a[2], a[3], q[0], q[1], q[2], q[3], F[2 * de + 1], F[2 * de]);
        else if (de >= 0) mma(a[0], a[1], a[2], a[3], q[0], q[1], q[2], q[3], F[2 * de + 1], F[2 * de]);
      }
    }
#pragma unroll
    for (int i = 0; i < 8; i++) acc[14 + (i >> 2)][i & 3] += acc[10 + (i >> 2)][i & 3];
    F[64] = lds32(fa + 32 * 64); F[65] = lds32(fa + 32 * 65);
    uint32_t qp = qa + 128 * 11, sta = st + 256 * 10;
    uint4* yd = ydst + 7 * 32;
#pragma unroll
    for (int i = 0; i < 6; i++) ldsm4(qd[i], qp - 16 * i);
    uint2 sv = lds64(sta + 256);
    float ci[4] = {bf_lo(sv.x), bf_hi(sv.x), bf_lo(sv.y), bf_hi(sv.y)};
    float T[5][4];
#pragma unroll
    for (int i = 0; i < 16; i++) T[i >> 2][i & 3] = acc[12 + (i >> 2)][i & 3];
    nb_sync(NB_YZ, 160);
    TS(46);
#pragma unroll 1
    for (int bp = 5; bp >= 0; bp--) {
      uint32_t held[2];
#pragma unroll
      for (int o = 1; o >= 0; o--) {
#pragma unroll
        for (int k = 4; k >= 1; k--) mmac(T[k], qd[0][0], qd[0][1], qd[0][2], qd[0][3], F[16 * k + 1], F[16 * k], T[k - 1]);
        mmac(T[0], qd[0][0], qd[0][1], qd[0][2], qd[0][3], F[1], F[0], ci);
        ldsm4(qd[6], qp - 16 * 6);
        ldsm4(qd[7], qp - 16 * 7);
        sv = lds64(sta);
#pragma unroll
        for (int i = 1; i < 8; i++) {
#pragma unroll
          for (int k = 3; k >= 0; k--)
            mma(T[k][0], T[k][1], T[k][2], T[k][3], qd[i][0], qd[i][1], qd[i][2], qd[i][3], F[16 * k + 2 * i + 1], F[16 * k + 2 * i]);
          if (i < 7) ldsm4(qd[i - 1], qp - 128 - 16 * (i - 1));
          if (i == 2) {
            const uint32_t w0 = pack_bf(T[4][0], T[4][1]), w1 = pack_bf(T[4][2], T[4][3]);
            if (o) { held[0] = w0; held[1] = w1; }
            else st_x(yd, nz(w0), w1, held[0], held[1]);
          }
          if (i == 4) {
            if (2 * bp + o <= 4) sv = make_uint2(0, 0);
            ci[0] = bf_lo(sv.x); ci[1] = bf_hi(sv.x); ci[2] = bf_lo(sv.y); ci[3] = bf_hi(sv.y);
          }
        }
        qp -= 128; sta -= 256;
      }
      yd -= 32;
    }
#pragma unroll
    for (int B = 1; B >= 0; B--)
      st_x(ydst + B * 32, nz(pack_bf(T[2 * B][0], T[2 * B][1])), pack_bf(T[2 * B][2], T[2 * B][3]),
           pack_bf(T[2 * B + 1][0], T[2 * B + 1][1]), pack_bf(T[2 * B + 1][2], T[2 * B + 1][3]));
  }
}

__device__ __forceinline__ void dual_exp(const uint32_t* w, uint32_t* e) {
  const float L = 1.44268798828125f;
  uint32_t mx = bmax2(bmax2(w[0], w[1]), bmax2(w[2], w[3]));
  uint32_t mn = bmin2(bmin2(w[0], w[1]), bmin2(w[2], w[3]));
  mx = bmax2(mx, __shfl_xor_sync(0xffffffffu, mx, 1));
  mn = bmin2(mn, __shfl_xor_sync(0xffffffffu, mn, 1));
  mx = bmax2(mx, __shfl_xor_sync(0xffffffffu, mx, 2));
  mn = bmin2(mn, __shfl_xor_sync(0xffffffffu, mn, 2));
  const float mx0 = bf_lo(mx) * -L, mx1 = bf_hi(mx) * -L, mn0 = bf_lo(mn) * L, mn1 = bf_hi(mn) * L;
#pragma unroll
  for (int i = 0; i < 2; i++) {
    const float a0 = bf_lo(w[2 * i]), a1 = bf_hi(w[2 * i]), b0 = bf_lo(w[2 * i + 1]), b1 = bf_hi(w[2 * i + 1]);
    e[2 * i] = pack_bf(ex2(fmaf(a0, L, mx0)), ex2(fmaf(b0, L, mx0)));
    e[2 * i + 1] = pack_bf(ex2(fmaf(a1, L, mx1)), ex2(fmaf(b1, L, mx1)));
    e[4 + 2 * i] = pack_bf(ex2(fmaf(a0, -L, mn0)), ex2(fmaf(b0, -L, mn0)));
    e[5 + 2 * i] = pack_bf(ex2(fmaf(a1, -L, mn1)), ex2(fmaf(b1, -L, mn1)));
  }
}
__device__ __forceinline__ void normalise(uint32_t* e, const float (&s)[4]) {
  const uint32_t r = pack_bf(rcp(s[0]), rcp(s[2]));
  const __nv_bfloat162 rr = *(const __nv_bfloat162*)&r;
#pragma unroll
  for (int i = 0; i < 4; i++) {
    const __nv_bfloat162 v = __hmul2(*(const __nv_bfloat162*)&e[i], (i & 1) ? __high2bfloat162(rr) : __low2bfloat162(rr));
    e[i] = *(const uint32_t*)&v;
  }
}
__host__ __device__ constexpr uint64_t qdesc(uint32_t addr) { return mkdesc(addr, 128, 256, 0); }

__global__ void __launch_bounds__(NTHREADS, 1)
fused_kernel(const Params P, const __grid_constant__ CUtensorMap mx, const __grid_constant__ CUtensorMap mw,
             const __grid_constant__ CUtensorMap mo, const __grid_constant__ CUtensorMap mu,
             const __grid_constant__ CUtensorMap mout, const __grid_constant__ CUtensorMap mw4) {
  constexpr uint32_t sb = SB;
  const int tid = threadIdx.x, lane = tid & 31;
  const int warp = __shfl_sync(0xffffffffu, tid >> 5, 0);
  const int b = blockIdx.x, oct = b >> 3, i8 = b & 7;
  const int rt = (((oct & 4) ? ~oct : oct) & 3) * 2 + (i8 >> 2);
  const int hp = (oct >> 2) * 4 + (i8 & 3);

  const int wg = warp >> 2, w = warp & 3;
  const int d = b * 4 + ((tid >> 5) & 3);
  const KgenRaw raw = kgen_load(P, d, tid >> 7, lane);
  const unsigned short dsk = __ldg((const unsigned short*)P.Dskip + d);
  if (tid < 384) {
    asm volatile("prefetch.tensormap [%0];" ::"l"(&mu) : "memory");
    asm volatile("prefetch.tensormap [%0];" ::"l"(&mw) : "memory");
    asm volatile("prefetch.tensormap [%0];" ::"l"(&mx) : "memory");
    asm volatile("prefetch.tensormap [%0];" ::"l"(&mw4) : "memory");
  }
  if (warp == 12) {
    if (lane == 0) {
#pragma unroll
      for (int i = 0; i < 9; i++) mbar_init(BAR(i), 1);
      asm volatile("fence.mbarrier_init.release.cluster;" ::: "memory");
    }
    __syncwarp();
    if (lane < 9) mbar_expect(BAR(0) + 8 * lane, (lane == 5 || lane == 7) ? 40960 : ((lane == 0 || lane > 5) ? 16384 : 28672));
    __syncwarp();
    e_tma3d(sb + OFF_W, &mw, BAR(MB_FULL), hp * 32, 0, 0);
    e_tma2d(sb + OFF_X + 3 * 16384, &mx, BAR(MB_FULL), 0, rt * 256);
    nb_arrive(NB_PROD, 192);
  } else if (warp == 14) {
    e_prefetch(P.x + (size_t)(rt * 256 + hp * 8) * 512, 8192);
  } else if (warp == 13) {
    if (lane == 0) {
#pragma unroll
      for (int i = 9; i < 39; i++) mbar_init(BAR(i), i < MB_EMPTY ? 1 : (i < MB_AUX ? 4 : 8));
      asm volatile("fence.mbarrier_init.release.cluster;" ::: "memory");
    }
    __syncwarp();
    if (lane < 13 && lane != 9) mbar_expect(BAR(MB_FULL + 8) + 8 * lane, lane < 8 ? 16384 : (lane == 8 ? 131072 : (lane == 10 ? 8192 : (lane == 11 ? 24576 : 32768))));
    nb_arrive(NB_PROD, 192);
  }
  const uint32_t tb = sb + OFF_T + w * T_CH;
  const uint32_t kp = wg >= 2 ? sb + OFF_STG0 + 16384 + w * 2048 : ((tb + 127) & ~127u) + wg * 2048;
  const KgenAddr kad = kgen_addr(lane, wg == 3 ? sb + OFF_X + 32768 + w * 2048 : kp);
  if (wg == 1) nb_sync(NB_PROD, 192);
  if (warp == 12) {
#pragma unroll 1
    for (int kb = 1; kb < 4; kb++) {
      if (kb == U_AT) e_tma4d(sb + OFF_STG0, &mu, BAR(MB_URAW), i8 * 64, oct * 2);
      e_tma3d(sb + OFF_W + kb * 12288, &mw, BAR(MB_FULL) + 8 * kb, hp * 32, kb * 64, 0);
      e_tma2d(sb + OFF_X + (kb < 2 ? kb + 3 : kb - 2) * 16384, &mx, BAR(MB_FULL) + 8 * kb, kb * 64, rt * 256);
    }
    e_tma4d(sb + OFF_W + 4 * 12288, &mw4, BAR(MB_FULL + 4), hp * 32, 4);
    e_tma4d(sb + OFF_W + 6 * 12288, &mw4, BAR(MB_FULL + 6), hp * 32, 6);
    if (smem_u32(smem_raw) != SB) __trap();
    if (lane == 0) TS1(54);
  }
  float k[5][4], k2048, ksc;
  kgen_unit(raw, kad, blockIdx.y, k, k2048, ksc);
  TS(40 + wg);
  if ((fu(k[0][0]) & fu(k[1][0]) & fu(k[2][0]) & fu(k[3][0]) & fu(k[4][0])) == 0xffffffffu) sts32(kp, 0);
  if (wg == 3) {
    nb_sync(0, 512);
    if (warp == 12) {
      asm volatile("fence.proxy.async.shared::cta;" ::: "memory");
      e_tma2d(sb + OFF_X + 2 * 16384, &mx, BAR(MB_FULL + 4), 256, rt * 256);
      if (X2_AT < 0) e_prefetch(P.x + (size_t)(rt * 256 + 128 + hp * 8) * 512, 8192);
    }
  } else if (wg) {
    nb_arrive(0, 512);
  }
  k2048 += __shfl_xor_sync(0xffffffffu, k2048, 16);
  k2048 += __shfl_xor_sync(0xffffffffu, k2048, 8);
  if (wg != 2) {
    uint32_t h[10];
#pragma unroll
    for (int j = 0; j < 10; j++) h[j] = hu(__floats2half2_rn(k[j >> 1][2 * (j & 1)], k[j >> 1][2 * (j & 1) + 1]));
    sts128(kp + lane * 16, h[0], h[1], h[2], h[3]);
    sts128(kp + 512 + lane * 16, h[4], h[5], h[6], h[7]);
    sts128(kp + 1024 + lane * 16, h[8], h[9], fu(k2048), fu(ksc));
  }
  if (wg == 0) { nb_arrive(NB_PREP, 512); nb_sync(0, 512); }
  else if (wg != 2) nb_arrive(NB_PREP, 512);
  else nb_sync(NB_PREP, 512);
  if (warp >= 12) {
    asm volatile("setmaxnreg.dec.sync.aligned.u32 32;");
    if (warp == 12) {
      uint32_t slot = sb + OFF_X + 3 * 16384;
#pragma unroll 1
      for (int n = 0; n < 11; n++) {
        mbar_spin(BAR(MB_EMPTY) + 8 * n);
        const int m = n + 5;
        e_tma2d(slot, &mx, BAR(MB_FULL) + 8 * m, (m & 7) * 64, rt * 256 + (m >> 3) * 128);
        slot = slot == sb + OFF_X + 4 * 16384 ? sb + OFF_X : slot + 16384;
        if (n == X2_AT) e_prefetch(P.x + (size_t)(rt * 256 + 128 + hp * 8) * 512, 8192);
        if (n == 7) {
          e_prefetch(P.wo + (size_t)b * 2048, 4096);
          asm volatile("prefetch.tensormap [%0];" ::"l"(&mo) : "memory");
          asm volatile("prefetch.tensormap [%0];" ::"l"(&mout) : "memory");
        }
      }
#pragma unroll 1
      for (int i = 0; i < 8; i++) {
        mbar_wait(BAR(MB_EMPTY + 10) + 8 * ((0x54332100u >> (4 * i)) & 7));
        const int w0 = (0x54736210u >> (4 * i)) & 7;
        e_tma3d(sb + OFF_W + w0 * 16384, &mo, BAR(MB_WO), 0, w0 * 64, (hp & 3) * 2);
      }
    } else {
      if (warp == 15) {
        const uint4 v0 = __ldg((const uint4*)P.wphi + hp * 64 + lane), v1 = __ldg((const uint4*)P.wphi + hp * 64 + 32 + lane);
        sts128(sb + OFF_PHI + (lane & 1) * 256 + (lane >> 1) * 16, v0.x, v0.y, v0.z, v0.w);
        sts128(sb + OFF_PHI + 512 + (lane & 1) * 256 + (lane >> 1) * 16, v1.x, v1.y, v1.z, v1.w);
        const uint32_t one = (((lane >> 3) ^ (lane >> 4)) & 1) ? 0u : ((lane & 1) ? 0x3F800000u : 0x3F80u);
        const int q = (lane >> 1) & 3;
        sts128(sb + OFF_EYE + lane * 16, q == 0 ? one : 0u, q == 1 ? one : 0u, q == 2 ? one : 0u, q == 3 ? one : 0u);
        sts64(sb + OFF_ONE + lane * 8, 0x3F803F80u, 0x3F803F80u);
        asm volatile("fence.proxy.async.shared::cta;" ::: "memory");
        nb_arrive(NB_KREAD, 160);
      }
      uint32_t* cnt = (uint32_t*)(P.xs + X_CNT) + (warp == 13 ? i8 : (warp == 14 ? 8 + rt : 16 + oct)) * 32;
      const unsigned target = (ld_x32(cnt) & ~15u) + 16;
      if (warp != 14) {
        if (warp == 15) mbar_wait(BAR(MB_EMPTY + ZERO_STEP));
        uint4* pz = P.xs + (warp == 13 ? X_PART + (hp * 8 + rt) * 144 : X_Y + b * 1024) + lane;
#pragma unroll 1
        for (int i = (warp == 13 ? 144 : 1024) - lane; i > 0; i -= 32, pz += 32) st_x(pz, 0, 0, 0, 0);
      }
      if (warp == 15) __syncwarp();
      else nb_sync(warp == 13 ? NB_INIT : NB_ODONE, warp == 13 ? 160 : 288);
      if (lane == 0) asm volatile("red.release.gpu.global.add.u32 [%0], %1;" ::"l"(cnt), "r"(warp == 15 ? 2 : 1) : "memory");
      if (lane == 0) TS1(warp == 13 ? 50 : (warp == 14 ? 57 : 53));
      asm volatile("fence.proxy.async.shared::cta;" ::: "memory");
      if (warp == 13) cnt += ((lane & 1 ? b >> 4 : i8 ^ (lane & 4)) - i8) * 32;
#pragma unroll 1
      for (int i = 0; i < SPIN_MAX; i++) {
        unsigned v;
        asm volatile("ld.acquire.gpu.global.u32 %0, [%1];" : "=r"(v) : "l"(cnt) : "memory");
        if (__all_sync(0xffffffffu, (int)(v - target) >= 0)) break;
      }
      if (lane == 0) TS1(warp == 13 ? 51 : (warp == 14 ? 58 : 55));
      if (warp == 15) { nb_arrive(NB_YZ, 160); return; }
      asm volatile("fence.proxy.async.global;" ::: "memory");
      if (warp == 13) {
        mbar_wait(BAR(MB_EMPTY + 11));
        e_expect(BAR(MB_UFULL), 4 * U_CH);
        e_bulk(sb + OFF_U, P.xs + X_UT + b * (U_CH / 4), 4 * U_CH, BAR(MB_UFULL));
      } else {
        const uint4* src = P.xs + X_O + (rt * 4 + (hp >> 2)) * 4096;
        e_bulk(sb + OFF_X + 32768 + 57344, src + 3584, 8192, BAR(MB_OA));
        e_bulk(sb + OFF_X + 32768, src, 32768, BAR(MB_OC));
        e_bulk(sb + OFF_STG0, src + 3200, 6144, BAR(MB_OB));
        nb_sync(NB_BDONE, 288);
        asm volatile("fence.proxy.async.shared::cta;" ::: "memory");
        e_bulk(sb + OFF_U, src + 2048, 18432, BAR(MB_OB));
      }
    }
    return;
  }

  const int t = tid & 127;
  const int g = lane >> 2, c = lane & 3;
  {
    if (wg == 2) {
      asm volatile("setmaxnreg.inc.sync.aligned.u32 160;");
#pragma unroll
      for (int j = 0; j < 5; j++) { k[j][0] *= ksc; k[j][1] *= ksc; k[j][2] *= ksc; k[j][3] *= ksc; }
#pragma unroll 1
      for (int q = 0; q < 3; q++) {
        const uint32_t src = (q == 2 ? kp : ((tb + 127) & ~127u) + q * 2048) + lane * 16;
        const uint4 v0 = lds128(src), v1 = lds128(src + 512), v2 = lds128(src + 1024);
        const uint32_t h[10] = {v0.x, v0.y, v0.z, v0.w, v1.x, v1.y, v1.z, v1.w, v2.x, v2.y};
#pragma unroll
        for (int j = 0; j < 10; j++) {
          const float2 f = __half22float2(*(const __half2*)&h[j]);
          k[j >> 1][2 * (j & 1)] = fmaf(f.x, uf(v2.w), k[j >> 1][2 * (j & 1)]);
          k[j >> 1][2 * (j & 1) + 1] = fmaf(f.y, uf(v2.w), k[j >> 1][2 * (j & 1) + 1]);
        }
        k2048 += uf(v2.z);
      }
#pragma unroll
      for (int o2 = 4; o2; o2 >>= 1) k2048 += __shfl_xor_sync(0xffffffffu, k2048, o2);
      if (lane == 0) k[0][0] += bf_lo(dsk);
      __syncwarp();
      if (lane == 0) mbar_arrive(BAR(MB_AUX));
      TS(34);
      build_tables(tb, lane, k, k2048);
      TS(35);
      uint4* const g_y = P.xs + X_Y;
      conv_channel(sb + OFF_U + w * U_CH, tb, lane, g_y + (size_t)d * 256 + lane);
      nb_arrive(NB_BDONE, 288);
      TS(37);
      const int lam = w * 8 + g;
      const uint4* src = g_y + (size_t)(oct * 32 + c * 8) * 256 + i8 * 32 + lam;
      uint4 v[8];
#pragma unroll 1
      for (int it = 0; it < SPIN_MAX; it++) {
        uint32_t m = 0xffffffffu;
#pragma unroll
        for (int i = 0; i < 8; i++) v[i] = ld_x(src + i * 256);
#pragma unroll
        for (int i = 0; i < 8; i++) m = min(m, v[i].x);
        if (__all_sync(0xffffffffu, m != 0)) break;
      }
      __nv_bfloat16* dst = P.out + (size_t)(i8 * 256 + (lam >> 2) * 16 + (lam & 3) * 2) * 1024 + 512 + oct * 32 + c * 8;
#pragma unroll
      for (int i = 0; i < 8; i++) *(uint4*)(dst + (size_t)((i >> 2) * 128 + ((i >> 1) & 1) * 8 + (i & 1)) * 1024) = tr_row(v, i);
      TS(38);
      GT(63);
      if (w == 0) TSDUMP(32);
      return;
    }
    if (wg == 1) {
      mbar_wait(BAR(MB_URAW));
      TS(48);
      uint4* dst = P.xs + X_UT + (i8 * 64 + g) * (U_CH / 16) + (w & 1) * (U_ODD / 16) + U_PAD / 16 + oct * 8 + (w >> 1) * 4 + c;
      const int ln = ((lane >> 1) & 3) + 4 * (lane & 1);
      uint32_t r[8][4];
#pragma unroll
      for (int i = 0; i < 8; i++) ldsm4t(r[i], sb + OFF_STG0 + w * 4096 + ((lane >> 3) * 8 + ln) * 128 + ((i ^ ln) << 4));
#pragma unroll
      for (int i = 0; i < 8; i++) dst[i * (U_CH / 2)] = make_uint4(r[i][0], r[i][1], r[i][2], r[i][3]);
      nb_arrive(NB_INIT, 160);
      if (lane == 0) mbar_arrive(BAR(MB_AUX));
      mbar_wait(BAR(MB_EMPTY + 4));
      mbar_spin(BAR(MB_EMPTY + 6));
    }
    TS(wg * 16 + 1);
  }

  float acc[2][48];
  {
    uint32_t fb = BAR(MB_FULL) + 64 * wg;
    uint32_t da = (uint32_t)mkdesc(sb + OFF_X, 16, 0, 0) + (wg ? 1024 : 3072), db = (uint32_t)mkdesc(sb + OFF_W, 4096, 0, 0);
    constexpr uint64_t ha = mkdesc(0, 0, 1024, 1), hb = mkdesc(0, 0, 512, 2);
    mbar_spin(fb);
    TS(wg * 16 + 2);
#pragma unroll 1
    for (int kb = 0; kb < 8; kb++) {
      WG_FENCE();
#pragma unroll
      for (int k = 0; k < 4; k++) {
        wgmma_ss_n96(acc[0], ha | (da + 2 * k), hb | (db + 64 * k), k ? 1 : kb);
        wgmma_ss_n96(acc[1], ha | (da + 2 * k + 512), hb | (db + 64 * k), k ? 1 : kb);
      }
      WG_COMMIT();
      if (kb < 7) mbar_spin(fb + 8);
      WG_WAIT(1);
      if (kb > 0) e_arrive(fb + 8 * (MB_EMPTY - MB_FULL - 1));
      fb += 8; db += 768;
      da = da == (uint32_t)mkdesc(sb + OFF_X + 65536, 16, 0, 0) ? da - 4096 : da + 1024;
    }
    if (wg == 0) nb_sync(NB_KREAD, 160);
    WG_WAIT(0);
    e_arrive(fb + 8 * (MB_EMPTY - MB_FULL - 1));
    mbar_spin(fb + 8 * (MB_EMPTY - MB_FULL - 1));
  }
  TS(wg * 16 + 3);
  asm volatile("setmaxnreg.inc.sync.aligned.u32 160;");

  constexpr uint32_t stg0 = sb + OFF_STG0, stg1 = sb + OFF_X + 32768;
  uint4* const g_part = P.xs + X_PART;
  uint4* const g_o = P.xs + X_O;
  constexpr uint32_t kvs = stg0;
  auto pack8 = [](const float* a) { return make_uint4(pack_bf(a[0], a[1]), pack_bf(a[2], a[3]), pack_bf(a[4], a[5]), pack_bf(a[6], a[7])); };
  auto feat = [&](const uint4 (&af)[4], float (&p)[4][8]) {
    WG_FENCE();
#pragma unroll
    for (int u = 0; u < 4; u++) wgmma_rs_n16(p[u], af[u], qdesc(sb + OFF_PHI + (u & 1) * 512), 0);
    WG_COMMIT();
  };
  auto packp = [](const float (&p)[4][8], uint32_t (&pw)[16]) {
#pragma unroll
    for (int i = 0; i < 16; i++) pw[i] = pack_bf(p[i >> 2][(i & 1) + 2 * (i & 2)], p[i >> 2][(i & 1) + 2 * (i & 2) + 2]);
  };
  auto contract = [&](float (&kc)[20], uint32_t stg, int acc_in) {
    WG_FENCE();
#pragma unroll
    for (int s = 0; s < 8; s++) wgmma_ss_n40(kc, qdesc(stg + s * SLAB), qdesc(stg + s * SLAB + 2048), s ? 1 : acc_in);
    WG_COMMIT();
    WG_WAIT(0);
  };
  uint32_t eq[32];
  {
    uint4 af[4], aq[4], vp[4];
    float p[4][8];
#pragma unroll
    for (int u = 0; u < 4; u++) af[u] = pack8(acc[u >> 1] + 16 + 8 * (u & 1));
    feat(af, p);
#pragma unroll
    for (int u = 0; u < 4; u++) { aq[u] = pack8(acc[u >> 1] + 8 * (u & 1)); vp[u] = pack8(acc[u >> 1] + 32 + 8 * (u & 1)); }
    WG_WAIT(0);
    uint32_t pw[16], ek[32];
    packp(p, pw);
#pragma unroll
    for (int u = 0; u < 4; u++) dual_exp(pw + 4 * u, ek + 8 * u);
    TS(wg * 16 + 12);
    mbar_wait(BAR(MB_AUX));
    float rs[8][4];
    WG_FENCE();
#pragma unroll
    for (int i = 0; i < 8; i++) wgmma_rs_n8(rs[i], make_uint4(ek[4 * i], ek[4 * i + 1], ek[4 * i + 2], ek[4 * i + 3]), qdesc(sb + OFF_ONE), 0);
    WG_COMMIT();
    feat(aq, p);
    const uint32_t sl = (wg ? stg1 : stg0) + w * SLAB + lane * 16;
#pragma unroll
    for (int i = 0; i < 4; i++) stsm4(sl + (i >> 1) * 4 * SLAB + 2048 + (i & 1) * 512, vp[i].x, vp[i].y, vp[i].z, vp[i].w);
    sts128(sl + (lane >> 4) * (4 * SLAB - 256) + 3072, 0x3F803F80u, 0x3F803F80u, 0x3F803F80u, 0x3F803F80u);
    WG_WAIT(1);
#pragma unroll
    for (int i = 0; i < 8; i++) {
      normalise(ek + 4 * i, rs[i]);
      stsm4(sl + (i >> 2) * 4 * SLAB + (i & 3) * 512, ek[4 * i], ek[4 * i + 1], ek[4 * i + 2], ek[4 * i + 3]);
    }
    asm volatile("fence.proxy.async.shared::cta;" ::: "memory");
    TS(wg * 16 + 13);
    if (wg) {
      nb_arrive(NB_ST0, 256);
    } else {
      float kc[20];
      uint4* pp = g_part + (size_t)(hp * 8 + rt) * 144 + t;
      uint32_t* pz = (uint32_t*)(pp - t + 128) + w * 16 + c * 8 + g;
      asm volatile("" : "+l"(pp), "+l"(pz));
      nb_sync(NB_WG0, 128);
      contract(kc, stg0, 0);
      mbar_wait(BAR(MB_UFULL));
      TS(15);
      nb_sync(NB_ST0, 256);
      contract(kc, stg1, 1);
      TS(6);
      float kv[8];
#pragma unroll
      for (int i = 0; i < 8; i++) kv[i] = w & 2 ? kc[8 + i] : kc[i];
      st_x(pp, nz(pack_bf(kv[0], kv[1])), pack_bf(kv[2], kv[3]), pack_bf(kv[4], kv[5]), pack_bf(kv[6], kv[7]));
      if (c < 2) st_x32(pz, nz(fu(c ? kc[18] : kc[16])));
      TS(5);
    }
    SPLIT();
    WG_WAIT(0);
    packp(p, pw);
#pragma unroll
    for (int u = 0; u < 4; u++) dual_exp(pw + 4 * u, eq + 8 * u);
    SPLIT();
  }
  TS(wg * 16 + 4);
  if (wg == 1) {
    mbar_wait(BAR(MB_UFULL));
    const uint4* ps = g_part + (size_t)hp * 8 * 144 + t;
    const uint32_t* zs = (const uint32_t*)(g_part + (size_t)(hp * 8 + (lane >> 4) * 4) * 144 + 128) + w * 16 + (lane & 15);
    uint4 v[8];
    uint32_t zv[4];
#pragma unroll 1
    for (int it = 0; it < SPIN_MAX; it++) {
#pragma unroll
      for (int i = 0; i < 8; i++) v[i] = ld_x(ps + i * 144);
#pragma unroll
      for (int i = 0; i < 4; i++) zv[i] = ld_x32(zs + i * 576);
      uint32_t m = min(min(zv[0], zv[1]), min(zv[2], zv[3]));
#pragma unroll
      for (int i = 0; i < 8; i++) m = min(m, v[i].x);
      if (__all_sync(0xffffffffu, m != 0)) break;
    }
    float s[8];
    WG_FENCE();
#pragma unroll
    for (int r = 0; r < 8; r++) wgmma_rs_n16(s, v[r], qdesc(sb + OFF_EYE), r);
    WG_COMMIT();
    float zsum = (uf(zv[0]) + uf(zv[1])) + (uf(zv[2]) + uf(zv[3]));
    zsum += __shfl_xor_sync(0xffffffffu, zsum, 16);
    const uint32_t z1 = pack_bf(zsum, 1.f);
    if (lane < 16) sts128(kvs + w * 768 + 512 + lane * 16, z1, z1, z1, z1);
    WG_WAIT(0);
    stsm4(kvs + w * 768 + lane * 16, pack_bf(s[0], s[1]), pack_bf(s[2], s[3]), pack_bf(s[4], s[5]), pack_bf(s[6], s[7]));
    asm volatile("fence.proxy.async.shared::cta;" ::: "memory");
    TS(22);
  }
  nb_sync(NB_KV, 256);
  {
    float n[8][12];
    WG_FENCE();
#pragma unroll
    for (int i = 0; i < 8; i++) wgmma_rs_n24(n[i], make_uint4(eq[4 * i], eq[4 * i + 1], eq[4 * i + 2], eq[4 * i + 3]), qdesc(kvs + (i & 3) * 768), 0);
    WG_COMMIT();
    uint32_t* od = (uint32_t*)(g_o + (size_t)((rt * 4 + wg * 2) * 32 + hp * 2) * 128) + w * 64 + lane;
    WG_WAIT(0);
#pragma unroll
    for (int u = 0; u < 4; u++) {
      float(&np)[12] = n[2 * u];
      const float(&nm)[12] = n[2 * u + 1];
      const float q0 = np[9] * rcp(nm[9]), q1 = np[11] * rcp(nm[11]);
      const float r0 = rcp(fmaf(nm[8], q0, fmaf(np[9], 1e-6f, np[8]))), r1 = rcp(fmaf(nm[10], q1, fmaf(np[11], 1e-6f, np[10])));
#pragma unroll
      for (int i = 0; i < 8; i++) np[i] = fmaf(nm[i], (i & 2) ? q1 : q0, np[i]);
      uint32_t* o = od + (u >> 1) * 16384 + (u & 1) * 512;
      o[0] = pack_bf(np[0] * r0, np[1] * r0);
      o[32] = pack_bf(np[2] * r1, np[3] * r1);
      o[256] = pack_bf(np[4] * r0, np[5] * r0);
      o[288] = pack_bf(np[6] * r1, np[7] * r1);
      if (u == 1) SPLIT();
    }
  }
  TS(wg * 16 + 7);
  nb_arrive(NB_ODONE, 288);
  if (wg) { if (w == 0) TSDUMP(16); return; }
  mbar_wait(BAR(MB_WO));
  nb_sync(NB_BDONE, 288);
  TS(8);
  mbar_spin(BAR(MB_OA));
  TS(9);
  float oc[64];
  {
    constexpr uint64_t ha = mkdesc(0, 0, 128, 0), hb = mkdesc(0, 0, 1024, 1);
    constexpr uint32_t da0 = (uint32_t)mkdesc(stg1, 1024, 0, 0), db0 = (uint32_t)mkdesc(sb + OFF_W, 8192, 0, 0);
#pragma unroll 1
    for (int j = 0; j < 8; j++) {
      const int kb = (j + 7) & 7;
      if ((j & 3) == 1) mbar_spin(j == 1 ? BAR(MB_OC) : BAR(MB_OB));
      WG_FENCE();
#pragma unroll
      for (int k = 0; k < 4; k++) wgmma_ss_n128(oc, ha | (da0 + 512 * kb + 128 * k), hb | (db0 + 1024 * kb + 128 * k), k ? 1 : j);
      WG_COMMIT();
    }
    WG_WAIT(0);
  }
  TS(10);
  const uint32_t ot = ((sb + OFF_T + 1023) & ~1023u) + w * 4096;
#pragma unroll
  for (int hf = 0; hf < 2; hf++) {
#pragma unroll
    for (int i = 8 * hf; i < 8 * hf + 8; i += 2)
      stsm4(ot + hf * 2048 + (lane & 15) * 128 + (((i + (lane >> 4)) ^ lane) & 7) * 16, pack_bf(oc[4 * i], oc[4 * i + 1]),
            pack_bf(oc[4 * i + 2], oc[4 * i + 3]), pack_bf(oc[4 * i + 4], oc[4 * i + 5]), pack_bf(oc[4 * i + 6], oc[4 * i + 7]));
    asm volatile("fence.proxy.async.shared::cta;" ::: "memory");
    __syncwarp();
    e_store2d(&mout, ot + hf * 2048, (hp & 3) * 128 + hf * 64, (rt * 4 + (hp >> 2)) * 64 + w * 16);
  }
  asm volatile(ELECT "cp.async.bulk.commit_group;\n@p cp.async.bulk.wait_group.read 0;\n}\n" ::: "memory");
  TS(wg * 16 + 11);
  GT(61 + wg);
  if (w == 0) TSDUMP(0);
  if (w == 1) TSDUMP(48);
}

typedef CUresult (*EncodeFn)(CUtensorMap*, CUtensorMapDataType, cuuint32_t, void*, const cuuint64_t*, const cuuint64_t*,
                             const cuuint32_t*, const cuuint32_t*, CUtensorMapInterleave, CUtensorMapSwizzle,
                             CUtensorMapL2promotion, CUtensorMapFloatOOBfill);

}

extern "C" void kernel_launch(void* const* d_in, const int* in_sizes, int n_in, void* d_out, int out_size) {
  (void)in_sizes; (void)n_in; (void)out_size;
  void* fn = nullptr;
  cudaDriverEntryPointQueryResult qr;
  cudaGetDriverEntryPoint("cuTensorMapEncodeTiled", &fn, cudaEnableDefault, &qr);
  EncodeFn enc = (EncodeFn)fn;
  CUtensorMap mx, mw, mo, mu, mout, mw4;
  const cuuint32_t es[5] = {1, 1, 1, 1, 1};
  {
    cuuint64_t dims[2] = {512, 2048}, st[1] = {1024};
    cuuint32_t box[2] = {64, 128};
    enc(&mx, CU_TENSOR_MAP_DATA_TYPE_BFLOAT16, 2, d_in[0], dims, st, box, es, CU_TENSOR_MAP_INTERLEAVE_NONE,
        CU_TENSOR_MAP_SWIZZLE_128B, CU_TENSOR_MAP_L2_PROMOTION_L2_128B, CU_TENSOR_MAP_FLOAT_OOB_FILL_NONE);
  }
  {
    cuuint64_t dims[3] = {512, 512, 3}, st[2] = {3072, 1024};
    cuuint32_t box[3] = {32, 64, 3};
    enc(&mw, CU_TENSOR_MAP_DATA_TYPE_BFLOAT16, 3, d_in[1], dims, st, box, es, CU_TENSOR_MAP_INTERLEAVE_NONE,
        CU_TENSOR_MAP_SWIZZLE_64B, CU_TENSOR_MAP_L2_PROMOTION_L2_128B, CU_TENSOR_MAP_FLOAT_OOB_FILL_NONE);
  }
  {
    cuuint64_t dims[3] = {64, 512, 8}, st[2] = {1024, 128};
    cuuint32_t box[3] = {64, 64, 2};
    enc(&mo, CU_TENSOR_MAP_DATA_TYPE_BFLOAT16, 3, d_in[3], dims, st, box, es, CU_TENSOR_MAP_INTERLEAVE_NONE,
        CU_TENSOR_MAP_SWIZZLE_128B, CU_TENSOR_MAP_L2_PROMOTION_L2_128B, CU_TENSOR_MAP_FLOAT_OOB_FILL_NONE);
  }
  {
    cuuint64_t dims[4] = {512, 4, 16, 32}, st[3] = {16384, 1024, 65536};
    cuuint32_t box[4] = {64, 4, 16, 2};
    enc(&mu, CU_TENSOR_MAP_DATA_TYPE_BFLOAT16, 4, d_in[4], dims, st, box, es, CU_TENSOR_MAP_INTERLEAVE_NONE,
        CU_TENSOR_MAP_SWIZZLE_128B, CU_TENSOR_MAP_L2_PROMOTION_L2_128B, CU_TENSOR_MAP_FLOAT_OOB_FILL_NONE);
  }
  {
    cuuint64_t dims[2] = {1024, 2048}, st[1] = {2048};
    cuuint32_t box[2] = {64, 16};
    enc(&mout, CU_TENSOR_MAP_DATA_TYPE_BFLOAT16, 2, d_out, dims, st, box, es, CU_TENSOR_MAP_INTERLEAVE_NONE,
        CU_TENSOR_MAP_SWIZZLE_128B, CU_TENSOR_MAP_L2_PROMOTION_NONE, CU_TENSOR_MAP_FLOAT_OOB_FILL_NONE);
  }
  {
    cuuint64_t dims[4] = {512, 64, 3, 8}, st[3] = {3072, 1024, 64 * 3072};
    cuuint32_t box[4] = {32, 64, 3, 2};
    enc(&mw4, CU_TENSOR_MAP_DATA_TYPE_BFLOAT16, 4, d_in[1], dims, st, box, es, CU_TENSOR_MAP_INTERLEAVE_NONE,
        CU_TENSOR_MAP_SWIZZLE_64B, CU_TENSOR_MAP_L2_PROMOTION_L2_128B, CU_TENSOR_MAP_FLOAT_OOB_FILL_NONE);
  }
  Params P;
  P.x = (const __nv_bfloat16*)d_in[0];
  P.wphi = (const __nv_bfloat16*)d_in[2];
  P.wo = (const __nv_bfloat16*)d_in[3];
  P.logA = (const __nv_bfloat16*)d_in[5];
  P.Aim = (const __nv_bfloat16*)d_in[6];
  P.Cre = (const __nv_bfloat16*)d_in[7];
  P.Cim = (const __nv_bfloat16*)d_in[8];
  P.logdt = (const __nv_bfloat16*)d_in[9];
  P.Dskip = (const __nv_bfloat16*)d_in[10];
  P.out = (__nv_bfloat16*)d_out;
  cudaGetSymbolAddress((void**)&P.xs, g_x);
  P.ts = nullptr;
  cudaFuncSetAttribute(fused_kernel, cudaFuncAttributeMaxDynamicSharedMemorySize, SMEM_BYTES);
  fused_kernel<<<NCTA, NTHREADS, SMEM_BYTES>>>(P, mx, mw, mo, mu, mout, mw4);
}
```

```cpp
#include <cuda_runtime.h>
#include <cuda_bf16.h>
#include <cuda_fp16.h>
#include <cuda.h>
#include <stdint.h>

#define DBG_TS 0

namespace {

constexpr int NTHREADS = 512;
constexpr int NCTA = 128;
constexpr int OFF_W = 0;
constexpr int OFF_X = 98304;
constexpr int OFF_U = OFF_X + 65536;
constexpr int U_CH = 4416, U_ODD = 2240, U_PAD = 128;
constexpr int OFF_STG0 = OFF_U + 18432;
constexpr int SLAB = 3328;
constexpr int OFF_T = OFF_STG0 + 8 * SLAB;
constexpr int T_CH = 5216;
constexpr int T_D = 0;
constexpr int T_5 = 2144;
constexpr int T_3 = T_5 + 384;
constexpr int T_7 = T_5 + 1024;
constexpr int T_9 = T_7 + 320;
constexpr int T_KC = T_9 + 320;
constexpr int T_ST = T_5 - 1024;
constexpr int OFF_PHI = OFF_T + 4 * T_CH;
constexpr int OFF_EYE = OFF_PHI + 1024, OFF_ONE = OFF_EYE + 512;
constexpr int OFF_BAR = OFF_ONE + 256;
constexpr int SMEM_BYTES = OFF_BAR + 512 + 256 * DBG_TS;
constexpr uint32_t SB = 1024;
static_assert(T_KC + 2 * 656 <= T_CH, "table size");
static_assert(SMEM_BYTES <= 232448, "smem");
constexpr int MB_URAW = 0, MB_FULL = 1  , MB_WO = 17, MB_UFULL = 18, MB_OA = 19, MB_OB = 20, MB_OC = 21,
              MB_EMPTY = 22  , MB_AUX = 38;
__host__ __device__ constexpr uint32_t BAR(int i) { return SB + OFF_BAR + 8 * i; }
constexpr int NB_WG0 = 1, NB_ODONE = 2, NB_ST0 = 3  , NB_KV = 5, NB_YZ = 6, NB_INIT = 7, NB_PREP = 8, NB_PROD = 9, NB_KREAD = 10, NB_BDONE = 11;
#define X2_AT -1
#define U_AT 2
#define ZERO_STEP 12
constexpr int SPIN_MAX = 1 << 16;

constexpr int X_CNT = 0;
constexpr int X_PART = 256;
constexpr int X_O = X_PART + 16 * 8 * 144;
constexpr int X_Y = X_O + 32 * 32 * 128;
constexpr int X_UT = X_Y + 512 * 8 * 32;
constexpr int X_SIZE = X_UT + 512 * (U_CH / 16);
__device__ __align__(128) uint4 g_x[X_SIZE];
extern __shared__ uint8_t smem_raw[];
#define TS(i) do {} while (0)
#define TS1(i) do {} while (0)
#define GT(i) do {} while (0)
#define TSDUMP(base) do {} while (0)

__device__ __forceinline__ uint32_t smem_u32(const void* p) { return (uint32_t)__cvta_generic_to_shared(p); }
__device__ __forceinline__ void mbar_arrive(uint32_t b) {
  asm volatile("mbarrier.arrive.shared::cta.b64 _, [%0];" ::"r"(b) : "memory");
}
__device__ __forceinline__ void mbar_wait(uint32_t b) {
  uint32_t done = 0;
#pragma unroll 1
  for (int i = 0; i < SPIN_MAX && !done; i++) {
    asm volatile("{\n.reg .pred p;\nmbarrier.try_wait.parity.shared::cta.b64 p, [%1], 0, 4000;\nselp.u32 %0, 1, 0, p;\n}\n"
                 : "=r"(done) : "r"(b) : "memory");
  }
}
__device__ __forceinline__ void mbar_spin(uint32_t b) {
  uint32_t done = 0;
#pragma unroll 1
  for (int i = 0; i < (SPIN_MAX << 4) && !done; i++) {
    asm volatile("{\n.reg .pred p;\nmbarrier.try_wait.parity.shared::cta.b64 p, [%1], 0;\nselp.u32 %0, 1, 0, p;\n}\n"
                 : "=r"(done) : "r"(b) : "memory");
  }
}
__device__ __forceinline__ void mbar_init(uint32_t b, int n) {
  asm volatile("mbarrier.init.shared::cta.b64 [%0], %1;" ::"r"(b), "r"(n) : "memory");
}
__device__ __forceinline__ void mbar_expect(uint32_t b, int bytes) {
  asm volatile("mbarrier.arrive.expect_tx.shared::cta.b64 _, [%0], %1;" ::"r"(b), "r"(bytes) : "memory");
}
__device__ __forceinline__ void nb_sync(int id, int n) { asm volatile("bar.sync %0, %1;" ::"r"(id), "r"(n) : "memory"); }
__device__ __forceinline__ void nb_arrive(int id, int n) { asm volatile("bar.arrive %0, %1;" ::"r"(id), "r"(n) : "memory"); }
#define ELECT "{\n.reg .pred p;\nelect.sync _|p, 0xffffffff;\n@p "
__device__ __forceinline__ void e_arrive(uint32_t b) {
  asm volatile(ELECT "mbarrier.arrive.shared::cta.b64 _, [%0];\n}\n" ::"r"(b) : "memory");
}
__device__ __forceinline__ void e_expect(uint32_t b, int bytes) {
  asm volatile(ELECT "mbarrier.arrive.expect_tx.shared::cta.b64 _, [%0], %1;\n}\n" ::"r"(b), "r"(bytes) : "memory");
}
__device__ __forceinline__ void e_tma2d(uint32_t dst, const CUtensorMap* m, uint32_t bar, int c0, int c1) {
  asm volatile(ELECT "cp.async.bulk.tensor.2d.shared::cluster.global.mbarrier::complete_tx::bytes [%0], [%1, {%3,%4}], [%2];\n}\n"
               ::"r"(dst), "l"(m), "r"(bar), "r"(c0), "r"(c1) : "memory");
}
__device__ __forceinline__ void e_tma3d(uint32_t dst, const CUtensorMap* m, uint32_t bar, int c0, int c1, int c2) {
  asm volatile(ELECT "cp.async.bulk.tensor.3d.shared::cluster.global.mbarrier::complete_tx::bytes [%0], [%1, {%3,%4,%5}], [%2];\n}\n"
               ::"r"(dst), "l"(m), "r"(bar), "r"(c0), "r"(c1), "r"(c2) : "memory");
}
__device__ __forceinline__ void e_tma4d(uint32_t dst, const CUtensorMap* m, uint32_t bar, int c0, int c3) {
  asm volatile(ELECT "cp.async.bulk.tensor.4d.shared::cluster.global.mbarrier::complete_tx::bytes [%0], [%1, {%3,%5,%5,%4}], [%2];\n}\n"
               ::"r"(dst), "l"(m), "r"(bar), "r"(c0), "r"(c3), "r"(0) : "memory");
}
__device__ __forceinline__ void e_bulk(uint32_t dst, const void* src, int bytes, uint32_t bar) {
  asm volatile(ELECT "cp.async.bulk.shared::cluster.global.mbarrier::complete_tx::bytes [%0], [%1], %2, [%3];\n}\n"
               ::"r"(dst), "l"(src), "r"(bytes), "r"(bar) : "memory");
}
__device__ __forceinline__ void e_prefetch(const void* p, int bytes) {
  asm volatile(ELECT "cp.async.bulk.prefetch.L2.global [%0], %1;\n}\n" ::"l"(p), "r"(bytes) : "memory");
}
__device__ __forceinline__ void e_store2d(const CUtensorMap* m, uint32_t src, int c0, int c1) {
  asm volatile(ELECT "cp.async.bulk.tensor.2d.global.shared::cta.bulk_group [%0, {%2,%3}], [%1];\n}\n"
               ::"l"(m), "r"(src), "r"(c0), "r"(c1) : "memory");
}
__host__ __device__ constexpr uint64_t mkdesc(uint32_t addr, uint32_t lbo, uint32_t sbo, int swz) {
  return (uint64_t)((addr & 0x3FFFF) >> 4) | ((uint64_t)(lbo >> 4) << 16) | ((uint64_t)(sbo >> 4) << 32) |
         ((uint64_t)swz << 62);
}
#define SPLIT() asm volatile("{\n.reg .pred p;\nsetp.eq.u32 p, %0, %1;\n@p exit;\n}\n" ::"r"(blockIdx.y), "n"(__LINE__) : "memory")
#define WG_FENCE() asm volatile("wgmma.fence.sync.aligned;" ::: "memory")
#define WG_COMMIT() asm volatile("wgmma.commit_group.sync.aligned;" ::: "memory")
#define WG_WAIT(n) asm volatile("wgmma.wait_group.sync.aligned " #n ";" ::: "memory")

__device__ __forceinline__ void mma(float& d0, float& d1, float& d2, float& d3, uint32_t a0, uint32_t a1, uint32_t a2,
                                    uint32_t a3, uint32_t b0, uint32_t b1) {
  asm volatile("mma.sync.aligned.m16n8k16.row.col.f32.bf16.bf16.f32 {%0,%1,%2,%3},{%4,%5,%6,%7},{%8,%9},{%0,%1,%2,%3};"
               : "+f"(d0), "+f"(d1), "+f"(d2), "+f"(d3)
               : "r"(a0), "r"(a1), "r"(a2), "r"(a3), "r"(b0), "r"(b1));
}
__device__ __forceinline__ void mmac(float (&d)[4], uint32_t a0, uint32_t a1, uint32_t a2, uint32_t a3, uint32_t b0,
                                     uint32_t b1, const float (&c)[4]) {
  asm volatile("mma.sync.aligned.m16n8k16.row.col.f32.bf16.bf16.f32 {%0,%1,%2,%3},{%4,%5,%6,%7},{%8,%9},{%10,%11,%12,%13};"
               : "=f"(d[0]), "=f"(d[1]), "=f"(d[2]), "=f"(d[3])
               : "r"(a0), "r"(a1), "r"(a2), "r"(a3), "r"(b0), "r"(b1), "f"(c[0]), "f"(c[1]), "f"(c[2]), "f"(c[3]));
}
__device__ __forceinline__ void mma_p(int p, float (&d)[4], uint32_t a0, uint32_t a1, uint32_t a2, uint32_t a3, uint32_t b0, uint32_t b1) {
  asm volatile("{\n.reg .pred q;\nsetp.ne.b32 q, %10, 0;\n"
               "@q mma.sync.aligned.m16n8k16.row.col.f32.bf16.bf16.f32 {%0,%1,%2,%3},{%4,%5,%6,%7},{%8,%9},{%0,%1,%2,%3};\n}\n"
               : "+f"(d[0]), "+f"(d[1]), "+f"(d[2]), "+f"(d[3])
               : "r"(a0), "r"(a1), "r"(a2), "r"(a3), "r"(b0), "r"(b1), "r"(p));
}
__device__ __forceinline__ void mmac_p(int p, float (&d)[4], uint32_t a0, uint32_t a1, uint32_t a2, uint32_t a3, uint32_t b0,
                                       uint32_t b1, const float (&c)[4]) {
  asm volatile("{\n.reg .pred q;\nsetp.ne.b32 q, %14, 0;\n"
               "@q mma.sync.aligned.m16n8k16.row.col.f32.bf16.bf16.f32 {%0,%1,%2,%3},{%4,%5,%6,%7},{%8,%9},{%10,%11,%12,%13};\n}\n"
               : "+f"(d[0]), "+f"(d[1]), "+f"(d[2]), "+f"(d[3])
               : "r"(a0), "r"(a1), "r"(a2), "r"(a3), "r"(b0), "r"(b1), "f"(c[0]), "f"(c[1]), "f"(c[2]), "f"(c[3]), "r"(p));
}
__device__ __forceinline__ void mma_h(float (&d)[4], const uint32_t (&a)[4], uint32_t b0, uint32_t b1) {
  asm volatile("mma.sync.aligned.m16n8k16.row.col.f32.f16.f16.f32 {%0,%1,%2,%3},{%4,%5,%6,%7},{%8,%9},{%0,%1,%2,%3};"
               : "+f"(d[0]), "+f"(d[1]), "+f"(d[2]), "+f"(d[3]) : "r"(a[0]), "r"(a[1]), "r"(a[2]), "r"(a[3]), "r"(b0), "r"(b1));
}
__device__ __forceinline__ void mma0(float& d0, float& d1, float& d2, float& d3, uint32_t a0, uint32_t a1, uint32_t a2,
                                     uint32_t a3, uint32_t b0, uint32_t b1) {
  asm volatile("mma.sync.aligned.m16n8k16.row.col.f32.bf16.bf16.f32 {%0,%1,%2,%3},{%4,%5,%6,%7},{%8,%9},{%10,%10,%10,%10};"
               : "=f"(d0), "=f"(d1), "=f"(d2), "=f"(d3)
               : "r"(a0), "r"(a1), "r"(a2), "r"(a3), "r"(b0), "r"(b1), "f"(0.f));
}
__device__ __forceinline__ uint32_t pack_bf(float lo, float hi) {
  uint32_t r;
  asm("cvt.rn.bf16x2.f32 %0, %1, %2;" : "=r"(r) : "f"(hi), "f"(lo));
  return r;
}
__device__ __forceinline__ float bf_lo(uint32_t w) { return __uint_as_float(w << 16); }
__device__ __forceinline__ float bf_hi(uint32_t w) { return __uint_as_float(w & 0xffff0000u); }
__device__ __forceinline__ float bf_round(float x) { return __bfloat162float(__float2bfloat16_rn(x)); }
__device__ __forceinline__ uint32_t bmax2(uint32_t a, uint32_t b) {
  uint32_t r; asm("max.bf16x2 %0, %1, %2;" : "=r"(r) : "r"(a), "r"(b)); return r;
}
__device__ __forceinline__ uint32_t bmin2(uint32_t a, uint32_t b) {
  uint32_t r; asm("min.bf16x2 %0, %1, %2;" : "=r"(r) : "r"(a), "r"(b)); return r;
}
__device__ __forceinline__ float ex2(float x) { float r; asm("ex2.approx.ftz.f32 %0, %1;" : "=f"(r) : "f"(x)); return r; }
__device__ __forceinline__ float rcp(float x) { float r; asm("rcp.approx.ftz.f32 %0, %1;" : "=f"(r) : "f"(x)); return r; }
__device__ __forceinline__ void ldsm4(uint32_t (&r)[4], uint32_t a) {
  asm volatile("ldmatrix.sync.aligned.m8n8.x4.shared.b16 {%0,%1,%2,%3}, [%4];"
               : "=r"(r[0]), "=r"(r[1]), "=r"(r[2]), "=r"(r[3]) : "r"(a) : "memory");
}
__device__ __forceinline__ void ldsm4t(uint32_t (&r)[4], uint32_t a) {
  asm volatile("ldmatrix.sync.aligned.m8n8.x4.trans.shared.b16 {%0,%1,%2,%3}, [%4];"
               : "=r"(r[0]), "=r"(r[1]), "=r"(r[2]), "=r"(r[3]) : "r"(a) : "memory");
}
__device__ __forceinline__ void stsm4(uint32_t a, uint32_t r0, uint32_t r1, uint32_t r2, uint32_t r3) {
  asm volatile("stmatrix.sync.aligned.m8n8.x4.shared.b16 [%0], {%1,%2,%3,%4};"
               ::"r"(a), "r"(r0), "r"(r1), "r"(r2), "r"(r3) : "memory");
}
__device__ __forceinline__ uint32_t lds32(uint32_t a) {
  uint32_t r; asm volatile("ld.shared.u32 %0, [%1];" : "=r"(r) : "r"(a) : "memory"); return r;
}
__device__ __forceinline__ uint32_t lds16(uint32_t a) {
  uint32_t r; asm volatile("{\n.reg .u16 h;\nld.shared.u16 h, [%1];\ncvt.u32.u16 %0, h;\n}\n" : "=r"(r) : "r"(a) : "memory"); return r;
}
__device__ __forceinline__ uint2 lds64(uint32_t a) {
  uint2 r; asm volatile("ld.shared.v2.u32 {%0,%1}, [%2];" : "=r"(r.x), "=r"(r.y) : "r"(a) : "memory"); return r;
}
__device__ __forceinline__ uint4 lds128(uint32_t a) {
  uint4 r;
  asm volatile("ld.shared.v4.u32 {%0,%1,%2,%3}, [%4];" : "=r"(r.x), "=r"(r.y), "=r"(r.z), "=r"(r.w) : "r"(a) : "memory");
  return r;
}
__device__ __forceinline__ void sts32(uint32_t a, uint32_t v) { asm volatile("st.shared.u32 [%0], %1;" ::"r"(a), "r"(v) : "memory"); }
__device__ __forceinline__ void sts16(uint32_t a, uint32_t v) {
  asm volatile("{\n.reg .u16 h;\ncvt.u16.u32 h, %1;\nst.shared.u16 [%0], h;\n}\n" ::"r"(a), "r"(v) : "memory");
}
__device__ __forceinline__ void sts64(uint32_t a, uint32_t x, uint32_t y) {
  asm volatile("st.shared.v2.u32 [%0], {%1,%2};" ::"r"(a), "r"(x), "r"(y) : "memory");
}
__device__ __forceinline__ void sts128(uint32_t a, uint32_t x, uint32_t y, uint32_t z, uint32_t w) {
  asm volatile("st.shared.v4.u32 [%0], {%1,%2,%3,%4};" ::"r"(a), "r"(x), "r"(y), "r"(z), "r"(w) : "memory");
}
__device__ __forceinline__ uint4 ld_x(const uint4* p) {
  uint4 r;
  asm volatile("{\n.reg .b128 t;\nld.relaxed.gpu.global.b128 t, [%4];\nmov.b128 {%0,%1,%2,%3}, t;\n}\n"
               : "=r"(r.x), "=r"(r.y), "=r"(r.z), "=r"(r.w) : "l"(p) : "memory");
  return r;
}
__device__ __forceinline__ uint32_t ld_x32(const uint32_t* p) {
  uint32_t r; asm volatile("ld.relaxed.gpu.global.u32 %0, [%1];" : "=r"(r) : "l"(p) : "memory"); return r;
}
__device__ __forceinline__ void st_x(uint4* p, uint32_t x, uint32_t y, uint32_t z, uint32_t w) {
  asm volatile("{\n.reg .b128 t;\nmov.b128 t, {%1,%2,%3,%4};\nst.relaxed.gpu.global.b128 [%0], t;\n}\n"
               ::"l"(p), "r"(x), "r"(y), "r"(z), "r"(w) : "memory");
}
__device__ __forceinline__ void st_x_p(int p, uint4* a, uint32_t x, uint32_t y, uint32_t z, uint32_t w) {
  asm volatile("{\n.reg .b128 t;\n.reg .pred q;\nsetp.ne.b32 q, %5, 0;\nmov.b128 t, {%1,%2,%3,%4};\n@q st.relaxed.gpu.global.b128 [%0], t;\n}\n"
               ::"l"(a), "r"(x), "r"(y), "r"(z), "r"(w), "r"(p) : "memory");
}
__device__ __forceinline__ void sts64_p(int p, uint32_t a, uint32_t x, uint32_t y) {
  asm volatile("{\n.reg .pred q;\nsetp.ne.b32 q, %3, 0;\n@q st.shared.v2.u32 [%0], {%1,%2};\n}\n" ::"r"(a), "r"(x), "r"(y), "r"(p) : "memory");
}
__device__ __forceinline__ void st_x32(uint32_t* p, uint32_t x) {
  asm volatile("st.relaxed.gpu.global.u32 [%0], %1;" ::"l"(p), "r"(x) : "memory");
}
__device__ __forceinline__ uint32_t nz(uint32_t w) { return max(w, 1u); }
__device__ __forceinline__ uint32_t fu(float x) { return __float_as_uint(x); }
__device__ __forceinline__ float uf(uint32_t x) { return __uint_as_float(x); }

__device__ __forceinline__ void wgmma_ss_n96(float (&d)[48], uint64_t da, uint64_t db, int sc) {
  asm volatile("{\n.reg .pred p;\nsetp.ne.b32 p, %50, 0;\n"
      "wgmma.mma_async.sync.aligned.m64n96k16.f32.bf16.bf16 "
      "{%0,%1,%2,%3,%4,%5,%6,%7,%8,%9,%10,%11,%12,%13,%14,%15,%16,%17,%18,%19,%20,%21,%22,%23,%24,%25,%26,%27,%28,%29,%30,%31,%32,%33,%34,%35,%36,%37,%38,%39,%40,%41,%42,%43,%44,%45,%46,%47}, "
      "%48, %49, p, 1, 1, 0, 1;\n}\n"
      : "+f"(d[0]), "+f"(d[1]), "+f"(d[2]), "+f"(d[3]), "+f"(d[4]), "+f"(d[5]), "+f"(d[6]), "+f"(d[7]),
        "+f"(d[8]), "+f"(d[9]), "+f"(d[10]), "+f"(d[11]), "+f"(d[12]), "+f"(d[13]), "+f"(d[14]), "+f"(d[15]),
        "+f"(d[16]), "+f"(d[17]), "+f"(d[18]), "+f"(d[19]), "+f"(d[20]), "+f"(d[21]), "+f"(d[22]), "+f"(d[23]),
        "+f"(d[24]), "+f"(d[25]), "+f"(d[26]), "+f"(d[27]), "+f"(d[28]), "+f"(d[29]), "+f"(d[30]), "+f"(d[31]),
        "+f"(d[32]), "+f"(d[33]), "+f"(d[34]), "+f"(d[35]), "+f"(d[36]), "+f"(d[37]), "+f"(d[38]), "+f"(d[39]),
        "+f"(d[40]), "+f"(d[41]), "+f"(d[42]), "+f"(d[43]), "+f"(d[44]), "+f"(d[45]), "+f"(d[46]), "+f"(d[47])
      : "l"(da), "l"(db), "r"(sc));
}

__device__ __forceinline__ void wgmma_ss_n128(float (&d)[64], uint64_t da, uint64_t db, int sc) {
  asm volatile("{\n.reg .pred p;\nsetp.ne.b32 p, %66, 0;\n"
      "wgmma.mma_async.sync.aligned.m64n128k16.f32.bf16.bf16 "
      "{%0,%1,%2,%3,%4,%5,%6,%7,%8,%9,%10,%11,%12,%13,%14,%15,%16,%17,%18,%19,%20,%21,%22,%23,%24,%25,%26,%27,%28,%29,%30,%31,%32,%33,%34,%35,%36,%37,%38,%39,%40,%41,%42,%43,%44,%45,%46,%47,%48,%49,%50,%51,%52,%53,%54,%55,%56,%57,%58,%59,%60,%61,%62,%63}, "
      "%64, %65, p, 1, 1, 0, 1;\n}\n"
      : "+f"(d[0]), "+f"(d[1]), "+f"(d[2]), "+f"(d[3]), "+f"(d[4]), "+f"(d[5]), "+f"(d[6]), "+f"(d[7]),
        "+f"(d[8]), "+f"(d[9]), "+f"(d[10]), "+f"(d[11]), "+f"(d[12]), "+f"(d[13]), "+f"(d[14]), "+f"(d[15]),
        "+f"(d[16]), "+f"(d[17]), "+f"(d[18]), "+f"(d[19]), "+f"(d[20]), "+f"(d[21]), "+f"(d[22]), "+f"(d[23]),
        "+f"(d[24]), "+f"(d[25]), "+f"(d[26]), "+f"(d[27]), "+f"(d[28]), "+f"(d[29]), "+f"(d[30]), "+f"(d[31]),
        "+f"(d[32]), "+f"(d[33]), "+f"(d[34]), "+f"(d[35]), "+f"(d[36]), "+f"(d[37]), "+f"(d[38]), "+f"(d[39]),
        "+f"(d[40]), "+f"(d[41]), "+f"(d[42]), "+f"(d[43]), "+f"(d[44]), "+f"(d[45]), "+f"(d[46]), "+f"(d[47]),
        "+f"(d[48]), "+f"(d[49]), "+f"(d[50]), "+f"(d[51]), "+f"(d[52]), "+f"(d[53]), "+f"(d[54]), "+f"(d[55]),
        "+f"(d[56]), "+f"(d[57]), "+f"(d[58]), "+f"(d[59]), "+f"(d[60]), "+f"(d[61]), "+f"(d[62]), "+f"(d[63])
      : "l"(da), "l"(db), "r"(sc));
}

__device__ __forceinline__ void wgmma_ss_n40(float (&d)[20], uint64_t da, uint64_t db, int sc) {
  asm volatile("{\n.reg .pred p;\nsetp.ne.b32 p, %22, 0;\n"
      "wgmma.mma_async.sync.aligned.m64n40k16.f32.bf16.bf16 "
      "{%0,%1,%2,%3,%4,%5,%6,%7,%8,%9,%10,%11,%12,%13,%14,%15,%16,%17,%18,%19}, "
      "%20, %21, p, 1, 1, 1, 1;\n}\n"
      : "+f"(d[0]), "+f"(d[1]), "+f"(d[2]), "+f"(d[3]), "+f"(d[4]), "+f"(d[5]), "+f"(d[6]), "+f"(d[7]),
        "+f"(d[8]), "+f"(d[9]), "+f"(d[10]), "+f"(d[11]), "+f"(d[12]), "+f"(d[13]), "+f"(d[14]), "+f"(d[15]),
        "+f"(d[16]), "+f"(d[17]), "+f"(d[18]), "+f"(d[19])
      : "l"(da), "l"(db), "r"(sc));
}

__device__ __forceinline__ void wgmma_rs_n8(float (&d)[4], const uint4& a, uint64_t db, int sc) {
  asm volatile("{\n.reg .pred p;\nsetp.ne.b32 p, %9, 0;\n"
      "wgmma.mma_async.sync.aligned.m64n8k16.f32.bf16.bf16 "
      "{%0,%1,%2,%3}, "
      "{%4,%5,%6,%7}, %8, p, 1, 1, 1;\n}\n"
      : "+f"(d[0]), "+f"(d[1]), "+f"(d[2]), "+f"(d[3])
      : "r"(a.x), "r"(a.y), "r"(a.z), "r"(a.w), "l"(db), "r"(sc));
}

__device__ __forceinline__ void wgmma_rs_n16(float (&d)[8], const uint4& a, uint64_t db, int sc) {
  asm volatile("{\n.reg .pred p;\nsetp.ne.b32 p, %13, 0;\n"
      "wgmma.mma_async.sync.aligned.m64n16k16.f32.bf16.bf16 "
      "{%0,%1,%2,%3,%4,%5,%6,%7}, "
      "{%8,%9,%10,%11}, %12, p, 1, 1, 1;\n}\n"
      : "+f"(d[0]), "+f"(d[1]), "+f"(d[2]), "+f"(d[3]), "+f"(d[4]), "+f"(d[5]), "+f"(d[6]), "+f"(d[7])
      : "r"(a.x), "r"(a.y), "r"(a.z), "r"(a.w), "l"(db), "r"(sc));
}

__device__ __forceinline__ void wgmma_rs_n24(float (&d)[12], const uint4& a, uint64_t db, int sc) {
  asm volatile("{\n.reg .pred p;\nsetp.ne.b32 p, %17, 0;\n"
      "wgmma.mma_async.sync.aligned.m64n24k16.f32.bf16.bf16 "
      "{%0,%1,%2,%3,%4,%5,%6,%7,%8,%9,%10,%11}, "
      "{%12,%13,%14,%15}, %16, p, 1, 1, 1;\n}\n"
      : "+f"(d[0]), "+f"(d[1]), "+f"(d[2]), "+f"(d[3]), "+f"(d[4]), "+f"(d[5]), "+f"(d[6]), "+f"(d[7]),
        "+f"(d[8]), "+f"(d[9]), "+f"(d[10]), "+f"(d[11])
      : "r"(a.x), "r"(a.y), "r"(a.z), "r"(a.w), "l"(db), "r"(sc));
}

struct Params {
  const __nv_bfloat16 *logA, *Aim, *Cre, *Cim, *logdt, *Dskip, *x, *wphi, *wo;
  __nv_bfloat16* out;
  uint4* xs;
  long long* ts;
};

__device__ __forceinline__ uint4 tr_row(const uint4 (&v)[8], int i) {
  uint32_t o[4];
#pragma unroll
  for (int m = 0; m < 4; m++) {
    const uint4 &ra = v[2 * m], &rb = v[2 * m + 1];
    const int k = i >> 1;
    const uint32_t xa = k == 0 ? ra.x : k == 1 ? ra.y : k == 2 ? ra.z : ra.w;
    const uint32_t xb = k == 0 ? rb.x : k == 1 ? rb.y : k == 2 ? rb.z : rb.w;
    o[m] = __byte_perm(xa, xb, (i & 1) ? 0x7632 : 0x5410);
  }
  return make_uint4(o[0], o[1], o[2], o[3]);
}

struct cpx { float r, i; };
__device__ __forceinline__ cpx csq(cpx a) { return {a.r * a.r - a.i * a.i, 2.f * (a.r * a.i)}; }
__device__ __forceinline__ cpx polar(float e, float t) {
  const float m = ex2(e);
  return {m * __cosf(t), m * __sinf(t)};
}

struct KgenRaw { unsigned short la, ai, cr, ci, ldt; };
__device__ __forceinline__ KgenRaw kgen_load(const Params& P, int d, int unit, int lane) {
  const int o = d * 128 + unit * 32 + lane;
  return {__ldg((const unsigned short*)P.logA + o), __ldg((const unsigned short*)P.Aim + o), __ldg((const unsigned short*)P.Cre + o),
          __ldg((const unsigned short*)P.Cim + o), __ldg((const unsigned short*)P.logdt + d)};
}
struct hmul { __half2 a, b; };
__device__ __forceinline__ hmul mk_mul(cpx w) {
  uint32_t b;
  asm("{\n.reg .f32 n;\nneg.ftz.f32 n, %1;\ncvt.rn.f16x2.f32 %0, %2, n;\n}\n" : "=r"(b) : "f"(w.i), "f"(w.r));
  return {__floats2half2_rn(w.r, w.i), *(const __half2*)&b};
}
__device__ __forceinline__ __half2 hcm(__half2 z, const hmul& w) { return __hfma2(__high2half2(z), w.b, __hmul2(__low2half2(z), w.a)); }
__device__ __forceinline__ uint32_t hu(__half2 v) { return *(const uint32_t*)&v; }

struct KgenAddr { uint32_t sa, sb, lb, lc, la; };
__device__ __forceinline__ KgenAddr kgen_addr(int lane, uint32_t buf) {
  KgenAddr a;
  a.sa = buf + (lane & 7) * 128 + ((((lane >> 3) ^ lane) & 7) << 4);
  a.lb = buf + (lane >> 3) * 128 + (((lane ^ (lane >> 3)) & 7) << 4);
  a.la = buf + ((lane >> 3) & 1) * 1024 + (lane >> 4) * 128 + (((lane ^ (lane >> 4)) & 7) << 4);
  a.sb = a.sa ^ 64; a.lc = a.lb ^ 64;
  asm volatile("" : "+r"(a.sa), "+r"(a.sb), "+r"(a.lb), "+r"(a.lc), "+r"(a.la));
  return a;
}
__device__ __forceinline__ void kgen_unit(const KgenRaw& r, const KgenAddr& ad, uint32_t zero, float (&k)[5][4], float& k2048, float& sc) {
  const float dt = bf_round(expf(bf_lo(r.ldt)));
  const float a2 = bf_round(ex2(bf_lo(r.la) * 1.4426950408889634f)) * (dt * -1.4426950408889634f);
  const float f = bf_lo(r.ai) * dt;
  const float r128 = f * 20.371832715762604f;
  const uint32_t ex = min(max(__reduce_max_sync(0xffffffffu, max(r.cr & 0x7fffu, r.ci & 0x7fffu)) >> 7, 1u), 253u);
  const float cs = uf((254u - ex) << 23);
  sc = 2.f * dt * uf(ex << 23);
  const cpx C = {bf_lo(r.cr) * cs, -bf_lo(r.ci) * cs};
  auto put = [&](const __half2 (&v)[8], uint32_t off) {
    stsm4(ad.sa + off, hu(v[0]), hu(v[1]), hu(v[2]), hu(v[3]));
    stsm4(ad.sb + off, hu(v[4]), hu(v[5]), hu(v[6]), hu(v[7]));
  };
  uint32_t A[4][4], B[5][2][4];
  auto get = [&](int j, uint32_t off) {
    __syncwarp();
    ldsm4(B[j][0], ad.lb + off);
    ldsm4(B[j][1], ad.lc + 512 + off);
  };
  auto tile = [&](int j) {
    k[j][0] = k[j][1] = k[j][2] = k[j][3] = 0.f;
#pragma unroll
    for (int s = 0; s < 4; s++) mma_h(k[j], A[s], B[j][s >> 1][2 * (s & 1)], B[j][s >> 1][2 * (s & 1) + 1]);
  };
  auto after = [&](cpx v, uint32_t dep) { return cpx{uf(fu(v.r) ^ (dep & zero)), v.i}; };
  const cpx w1 = polar(a2, f), w128 = polar(a2 * 128.f, (r128 - rintf(r128)) * 6.283185307179586f);
  const cpx w2 = csq(w1), w4 = csq(w2);
  __half2 t0[8], t1[8], t2[8], t3[8], t4[8];
  const hmul m2 = mk_mul(w2), m4 = mk_mul(w4), m128 = mk_mul(w128);
  t0[0] = __floats2half2_rn(1.f, 0.f); t0[1] = __floats2half2_rn(w1.r, w1.i); t0[2] = m2.a; t0[4] = m4.a;
  t0[3] = hcm(t0[1], m2); t0[5] = hcm(t0[1], m4); t0[6] = hcm(t0[2], m4); t0[7] = hcm(t0[3], m4);
  put(t0, 0); get(0, 0);
  t1[0] = m128.a;
#pragma unroll
  for (int i = 1; i < 8; i++) t1[i] = hcm(t0[i], m128);
  put(t1, 1024); get(1, 1024);
  {
    cpx w8 = csq(after(w4, B[0][0][0]));
    w8.i = -w8.i;
    const cpx w16 = csq(w8), w32 = csq(w16), w64 = csq(w32);
    const hmul m8 = mk_mul(w8), m16 = mk_mul(w16), m32 = mk_mul(w32), m64 = mk_mul(w64);
    __half2 a[8];
    a[0] = __floats2half2_rn(C.r, C.i); a[1] = hcm(a[0], m8);
    a[2] = hcm(a[0], m16); a[3] = hcm(a[1], m16);
#pragma unroll
    for (int i = 0; i < 4; i++) a[4 + i] = hcm(a[i], m32);
    put(a, 0);
#pragma unroll
    for (int i = 0; i < 8; i++) a[i] = hcm(a[i], m64);
    put(a, 1024);
    __syncwarp();
#pragma unroll
    for (int s = 0; s < 4; s++) ldsm4(A[s], (ad.la ^ (s << 5)) + s * 256);
  }
  const cpx w256 = csq(after(w128, B[1][0][0]));
  const hmul m256 = mk_mul(w256);
  t2[0] = m256.a;
#pragma unroll
  for (int i = 1; i < 8; i++) t2[i] = hcm((i & 1) ? t1[i & 6] : t0[i & 6], m256);
  put(t2, 0); get(2, 0);
  tile(0); tile(1);
  const cpx w512 = csq(after(w256, A[0][0]));
  const hmul m512 = mk_mul(w512);
  t3[0] = m512.a;
#pragma unroll
  for (int i = 1; i < 8; i++) t3[i] = hcm((i & 2) ? t2[i & 5] : ((i & 1) ? t1[i & 4] : t0[i & 4]), m512);
  put(t3, 1024); get(3, 1024);
  tile(2);
  const cpx w1024 = csq(after(w512, B[2][0][0])), we = csq(w1024);
  const hmul m1024 = mk_mul(w1024);
  t4[0] = m1024.a;
#pragma unroll
  for (int i = 1; i < 8; i++) t4[i] = hcm((i & 4) ? t3[i & 3] : ((i & 2) ? t2[i & 1] : t1[0]), m1024);
  put(t4, 0); get(4, 0);
  tile(3); tile(4);
  k2048 = (C.r * we.r + C.i * we.i) * sc;
}

__device__ __forceinline__ void build_tables(uint32_t tb, int lane, float (&k)[5][4], float k2048) {
  const int g = lane >> 2, c = lane & 3;
  const uint32_t kc = tb + T_KC + 16;
  {
    const uint32_t a0 = kc + 16 * g + 4 * c, a2 = kc + 2 * (256 + 4 * g + c);
    const uint32_t a3 = kc + 2 * (384 + 2 * g + 64 * (c & 1) + (c >> 1)), a4 = kc + 2 * (512 + g + 32 * c);
#pragma unroll
    for (int r = 0; r < 2; r++) {
      sts32(a0 + 128 * r, pack_bf(k[0][2 * r], k[0][2 * r + 1]));
      sts32(a0 + 128 * r + 256, pack_bf(k[1][2 * r], k[1][2 * r + 1]));
      const uint32_t w2 = pack_bf(k[2][2 * r], k[2][2 * r + 1]);
      const uint32_t w3 = pack_bf(k[3][2 * r], k[3][2 * r + 1]);
      const uint32_t w4 = pack_bf(k[4][2 * r], k[4][2 * r + 1]);
      sts16(a2 + 64 * r, w2); sts16(a2 + 64 * r + 128, w2 >> 16);
      sts16(a3 + 32 * r, w3); sts16(a3 + 32 * r + 64, w3 >> 16);
      sts16(a4 + 16 * r, w4); sts16(a4 + 16 * r + 32, w4 >> 16);
    }
  }
  if (lane == 0) { sts16(kc + 2 * 640, pack_bf(k2048, 0.f)); sts32(kc - 4, 0); }
  __syncwarp();
  const uint32_t td = tb + T_D + 32;
#pragma unroll
  for (int hf = 0; hf < 2; hf++) {
    const uint2 v = lds64(kc + 256 * hf + 8 * lane);
    const uint32_t pv = lds32(kc + 256 * hf + 8 * lane - 4);
    sts128(td + 512 * hf + 16 * lane, __byte_perm(v.x, pv, 0x7610), __byte_perm(v.x, v.x, 0x1032), __byte_perm(v.y, v.x, 0x7610),
           __byte_perm(v.y, v.y, 0x1032));
  }
#pragma unroll
  for (int hf = 0; hf < 2; hf++) {
    const uint32_t v = lds32(kc + 512 + 128 * hf + 4 * lane), nx = lds32(kc + 516 + 128 * hf + 4 * lane);
    uint32_t w0 = __byte_perm(v, v, 0x1010);
    const uint32_t w1 = w0;
    if (hf == 0) { const uint32_t pv = lds32(kc + 508); if (lane == 0) w0 = __byte_perm(v, pv, 0x7610); }
    sts128(td + 1024 + 512 * hf + 16 * lane, w0, w1, __byte_perm(v, v, 0x1032), __byte_perm(nx, v, 0x7610));
  }
  {
    const uint32_t kk = lds16(kc + 2 * 384);
    const uint32_t w = lane < 3 ? (kk | (kk << 16)) : (lane == 3 ? (kk << 16) : 0u);
    if (lane < 24) sts32(td + 4 * (lane < 16 ? 512 + lane : lane - 24), w);
    const uint32_t lo_ = lds16(kc + 2 * 511), le_ = lds16(kc + 2 * 512);
    const uint32_t ja = tb + T_5 + (lane < 16 ? 4 * lane : 256 + 4 * lane);
    sts32(ja, lane == 16 ? (le_ << 16) : 0u);
    sts32(ja + 384, lane == 16 ? (lo_ << 16) : 0u);
    sts32(tb + (lane < 16 ? T_7 : T_9 - 64) + 4 * lane, 0u);
  }
#pragma unroll
  for (int s = 0; s < 2; s++) {
    const uint32_t b = kc + 2 * (s ? 512 : 384) + 8 * lane;
    const uint2 v = lds64(b);
    uint32_t em = lds16(b - 2), e0 = v.x;
    const uint32_t e4 = lds16(b + 8);
    if (lane == 0) { em = 0; e0 = 0; }
    sts64(tb + (s ? T_7 : T_3) + 64 + 8 * lane, __byte_perm(v.x, em, 0x5432), __byte_perm(v.y, v.x, 0x7632));
    sts64(tb + (s ? T_9 : T_5) + 64 + 8 * lane, __byte_perm(v.y, e0, 0x5410), __byte_perm(e4, v.y, 0x5410));
  }
  __syncwarp();
}

__device__ __forceinline__ uint32_t box2w(int lo, int n, int o) {
  return ((unsigned)(o - lo) < (unsigned)n ? 0x3F80u : 0u) | ((unsigned)(o + 1 - lo) < (unsigned)n ? 0x3F800000u : 0u);
}

__device__ __forceinline__ void conv_channel(uint32_t ub, uint32_t tb, int lane, uint4* ydst) {
  const int g = lane >> 2, c = lane & 3, x = g - 2 * c;
  const int mi = lane >> 3;
  const uint32_t qa = ub + U_PAD + 16 * (lane & 7) + ((mi == 0 || mi == 3) ? U_ODD : 0) - (mi == 0 ? 16 : 0);
  const uint32_t hb = ub + U_PAD + (mi & 1) * U_ODD + 16 * ((lane >> 4) + (lane & 7)) - 16;
  const uint32_t kv = lds16(tb + T_KC + 16 + 2 * 512);
  const int oh = c < 2 ? 8 + 2 * c : 2 * c - 8, og = c < 3 ? 2 * c : -10;
  uint32_t bx[4] = {box2w(g - 4, 9, 2 * c), box2w(g - 3, 7, 2 * c), box2w(g - 4, 9, oh), box2w(g - 3, 7, oh)};
  uint32_t by[4] = {box2w(g - 10, 5, 2 * c - 8), box2w(g - 5, 3, 2 * c - 8), box2w(g - 10, 5, og), box2w(g - 5, 3, og)};
  uint32_t lb0 = ((unsigned)(x + 5) < 2u ? kv : 0u) | ((unsigned)(x + 4) < 2u ? kv << 16 : 0u);
  uint32_t lb1 = ((unsigned)(x - 3) < 2u ? kv : 0u) | ((unsigned)(x - 4) < 2u ? kv << 16 : 0u);
  const int q0 = g - 1, q1 = c < 3 ? g : g - 2;
  uint32_t y0a = ub + U_PAD + (q0 & 1) * U_ODD + 16 * (q0 >> 1) + 4 * c;
  uint32_t y1a = ub + U_PAD + (q1 & 1) * U_ODD + 16 * (q1 >> 1) + 4 * c;
#pragma unroll
  for (int i = 0; i < 4; i++) asm volatile("" : "+r"(bx[i]), "+r"(by[i]));
  asm volatile("" : "+r"(lb0), "+r"(lb1), "+r"(y0a), "+r"(y1a));
  mbar_wait(BAR(MB_UFULL));
  mbar_spin(BAR(MB_EMPTY + 15));
  TS(36);
  float acc[16][4];
  {
    uint32_t z09[8], z07[8], zm9[8], zm7[8];
#pragma unroll
    for (int i = 0; i < 8; i++) {
      uint32_t h[4];
      ldsm4(h, hb + 128 * i);
      float y0, y1, y2, y3, w0, w1, w2, w3;
      mma0(y0, y1, y2, y3, bx[0], bx[1], bx[2], bx[3], h[2], c < 2 ? h[3] : h[1]);
      mma0(w0, w1, w2, w3, bx[0], bx[1], bx[2], bx[3], h[1], c < 2 ? h[2] : h[0]);
      z09[i] = pack_bf(y0, y1); z07[i] = pack_bf(y2, y3);
      zm9[i] = pack_bf(w0, w1); zm7[i] = pack_bf(w2, w3);
    }
  uint32_t f3[3][4][4];
  {
    const uint32_t fa = tb + T_7 + 4 * (16 + x);
#pragma unroll
    for (int tt = 0; tt < 3; tt++)
#pragma unroll
      for (int D = 0; D < 4; D++) {
        const uint32_t a = fa + (tt == 0 ? 316 : (tt == 1 ? 320 : 0)) + 64 * D;
        f3[tt][D][0] = lds32(a); f3[tt][D][1] = lds32(a + 32); f3[tt][D][2] = lds32(a - 32); f3[tt][D][3] = lds32(a);
      }
  }
    float a[4][2][4];
#pragma unroll
    for (int kap = 0; kap < 4; kap++)
#pragma unroll
      for (int sg = 0; sg < 2; sg++)
#pragma unroll
        for (int bk = 3; bk >= kap; bk--) {
          const uint32_t(&q0_)[4] = f3[sg ? 2 : 0][bk - kap];
          const uint32_t(&q1_)[4] = f3[sg ? 2 : 1][bk - kap];
          float(&a0)[4] = a[bk][0];
          float(&a1)[4] = a[bk][1];
          if (sg == 0 && kap == 0) {
            mma0(a0[0], a0[1], a0[2], a0[3], q0_[0], q0_[1], q0_[2], q0_[3], z09[0], z09[1]);
            mma0(a1[0], a1[1], a1[2], a1[3], q1_[0], q1_[1], q1_[2], q1_[3], zm9[0], zm9[1]);
          } else {
            mma(a0[0], a0[1], a0[2], a0[3], q0_[0], q0_[1], q0_[2], q0_[3], sg ? zm7[2 * kap] : z09[2 * kap], sg ? zm7[2 * kap + 1] : z09[2 * kap + 1]);
            mma(a1[0], a1[1], a1[2], a1[3], q1_[0], q1_[1], q1_[2], q1_[3], sg ? z07[2 * kap] : zm9[2 * kap], sg ? z07[2 * kap + 1] : zm9[2 * kap + 1]);
          }
        }
    SPLIT();
#pragma unroll
    for (int i = 0; i < 8; i++) {
      uint32_t h[4];
      ldsm4(h, qa + 128 * i);
      const float ci[4] = {a[i >> 1][0][2 * (i & 1)], a[i >> 1][0][2 * (i & 1) + 1], a[i >> 1][1][2 * (i & 1)], a[i >> 1][1][2 * (i & 1) + 1]};
      mmac(acc[8 + i], h[0], h[1], h[2], h[3], lb0, lb1, ci);
    }
  }
  TS(44);
  {
    uint2 a5[10], a3[10];
    const uint32_t aa = tb + T_5 + 4 * (8 + 2 * g - 2 * c);
#pragma unroll
    for (int m = 0; m < 10; m++) { a5[m] = lds64(aa + 32 * m); a3[m] = lds64(aa + 384 + 32 * m); }
    uint32_t x5[12][2], x3[12][2];
    auto ygen = [&](int kap) {
#pragma unroll
      for (int hh = 0; hh < 2; hh++) {
        float y0, y1, y2, y3;
        mma0(y0, y1, y2, y3, by[0], by[1], by[2], by[3], lds32(y0a + 128 * kap + 64 * hh), lds32(y1a + 128 * kap + 64 * hh));
        x5[kap][hh] = pack_bf(y0, y1);
        x3[kap][hh] = pack_bf(y2, y3);
      }
    };
    ygen(11); ygen(10); ygen(9); ygen(8);
#pragma unroll
    for (int kap = 11; kap >= 0; kap--) {
      if (kap >= 4) ygen(kap - 4);
#pragma unroll
      for (int sg = 0; sg < 2; sg++)
#pragma unroll
        for (int i = 4; i >= 0; i--) {
          const int be = kap + 4 + i;
          if (be <= 15) {
            const uint2 &hi = sg ? a3[2 * i + 1] : a5[2 * i + 1], &lo = sg ? a3[2 * i] : a5[2 * i];
            const uint32_t b0 = sg ? x3[kap][0] : x5[kap][0], b1 = sg ? x3[kap][1] : x5[kap][1];
            if (be < 8 && i == 0 && sg == 0) mma0(acc[be][0], acc[be][1], acc[be][2], acc[be][3], hi.x, hi.y, lo.x, lo.y, b0, b1);
            else mma(acc[be][0], acc[be][1], acc[be][2], acc[be][3], hi.x, hi.y, lo.x, lo.y, b0, b1);
          }
        }
    }
  }
  TS(45);
  {
    const uint32_t st = tb + T_ST + lane * 8;
#pragma unroll
    for (int be = 4; be < 12; be++) sts64(st + 256 * be, pack_bf(acc[be][0], acc[be][1]), pack_bf(acc[be][2], acc[be][3]));
    SPLIT();
    uint32_t F[66], qd[8][4];
    const uint32_t fa = tb + T_D + 32 + 4 * x;
#pragma unroll
    for (int i = 0; i < 32; i++) {
      const int s = 120 - (i >> 2) - 8 * (i & 3);
      uint32_t(&q)[4] = qd[i & 7];
      ldsm4(q, qa + 16 * s);
      const int m = 16 * (i & 3) + 2 * (i >> 2);
      F[m] = lds32(fa + 32 * m); F[m + 1] = lds32(fa + 32 * m + 32);
#pragma unroll
      for (int be = 15; be >= 12; be--) {
        const int de = 8 * be - s;
        float(&a)[4] = (be >= 14 && !(i & 1)) ? acc[be - 4] : acc[be];
        if (de >= 0 && be >= 14 && i == 2 * (15 - be)) mma0(a[0], a[1], a[2], a[3], q[0], q[1], q[2], q[3], F[2 * de + 1], F[2 * de]);
        else if (de >= 0) mma(a[0], a[1], a[2], a[3], q[0], q[1], q[2], q[3], F[2 * de + 1], F[2 * de]);
      }
    }
#pragma unroll
    for (int i = 0; i < 8; i++) acc[14 + (i >> 2)][i & 3] += acc[10 + (i >> 2)][i & 3];
    F[64] = lds32(fa + 32 * 64); F[65] = lds32(fa + 32 * 65);
    uint32_t qp = qa + 128 * 11, sta = st + 256 * 10;
    uint4* yd = ydst + 7 * 32;
#pragma unroll
    for (int i = 0; i < 6; i++) ldsm4(qd[i], qp - 16 * i);
    uint2 sv = lds64(sta + 256);
    float ci[4] = {bf_lo(sv.x), bf_hi(sv.x), bf_lo(sv.y), bf_hi(sv.y)};
    float T[5][4];
#pragma unroll
    for (int i = 0; i < 16; i++) T[i >> 2][i & 3] = acc[12 + (i >> 2)][i & 3];
    nb_sync(NB_YZ, 160);
    TS(46);
#pragma unroll 1
    for (int bp = 5; bp >= 0; bp--) {
      uint32_t held[2];
#pragma unroll
      for (int o = 1; o >= 0; o--) {
#pragma unroll
        for (int k = 4; k >= 1; k--) mmac(T[k], qd[0][0], qd[0][1], qd[0][2], qd[0][3], F[16 * k + 1], F[16 * k], T[k - 1]);
        mmac(T[0], qd[0][0], qd[0][1], qd[0][2], qd[0][3], F[1], F[0], ci);
        ldsm4(qd[6], qp - 16 * 6);
        ldsm4(qd[7], qp - 16 * 7);
        sv = lds64(sta);
#pragma unroll
        for (int i = 1; i < 8; i++) {
#pragma unroll
          for (int k = 3; k >= 0; k--)
            mma(T[k][0], T[k][1], T[k][2], T[k][3], qd[i][0], qd[i][1], qd[i][2], qd[i][3], F[16 * k + 2 * i + 1], F[16 * k + 2 * i]);
          if (i < 7) ldsm4(qd[i - 1], qp - 128 - 16 * (i - 1));
          if (i == 2) {
            const uint32_t w0 = pack_bf(T[4][0], T[4][1]), w1 = pack_bf(T[4][2], T[4][3]);
            if (o) { held[0] = w0; held[1] = w1; }
            else st_x(yd, nz(w0), w1, held[0], held[1]);
          }
          if (i == 4) {
            if (2 * bp + o <= 4) sv = make_uint2(0, 0);
            ci[0] = bf_lo(sv.x); ci[1] = bf_hi(sv.x); ci[2] = bf_lo(sv.y); ci[3] = bf_hi(sv.y);
          }
        }
        qp -= 128; sta -= 256;
      }
      yd -= 32;
    }
#pragma unroll
    for (int B = 1; B >= 0; B--)
      st_x(ydst + B * 32, nz(pack_bf(T[2 * B][0], T[2 * B][1])), pack_bf(T[2 * B][2], T[2 * B][3]),
           pack_bf(T[2 * B + 1][0], T[2 * B + 1][1]), pack_bf(T[2 * B + 1][2], T[2 * B + 1][3]));
  }
}

__device__ __forceinline__ void dual_exp(const uint32_t* w, uint32_t* e) {
  const float L = 1.44268798828125f;
  uint32_t mx = bmax2(bmax2(w[0], w[1]), bmax2(w[2], w[3]));
  uint32_t mn = bmin2(bmin2(w[0], w[1]), bmin2(w[2], w[3]));
  mx = bmax2(mx, __shfl_xor_sync(0xffffffffu, mx, 1));
  mn = bmin2(mn, __shfl_xor_sync(0xffffffffu, mn, 1));
  mx = bmax2(mx, __shfl_xor_sync(0xffffffffu, mx, 2));
  mn = bmin2(mn, __shfl_xor_sync(0xffffffffu, mn, 2));
  const float mx0 = bf_lo(mx) * -L, mx1 = bf_hi(mx) * -L, mn0 = bf_lo(mn) * L, mn1 = bf_hi(mn) * L;
#pragma unroll
  for (int i = 0; i < 2; i++) {
    const float a0 = bf_lo(w[2 * i]), a1 = bf_hi(w[2 * i]), b0 = bf_lo(w[2 * i + 1]), b1 = bf_hi(w[2 * i + 1]);
    e[2 * i] = pack_bf(ex2(fmaf(a0, L, mx0)), ex2(fmaf(b0, L, mx0)));
    e[2 * i + 1] = pack_bf(ex2(fmaf(a1, L, mx1)), ex2(fmaf(b1, L, mx1)));
    e[4 + 2 * i] = pack_bf(ex2(fmaf(a0, -L, mn0)), ex2(fmaf(b0, -L, mn0)));
    e[5 + 2 * i] = pack_bf(ex2(fmaf(a1, -L, mn1)), ex2(fmaf(b1, -L, mn1)));
  }
}
__device__ __forceinline__ void normalise(uint32_t* e, const float (&s)[4]) {
  const uint32_t r = pack_bf(rcp(s[0]), rcp(s[2]));
  const __nv_bfloat162 rr = *(const __nv_bfloat162*)&r;
#pragma unroll
  for (int i = 0; i < 4; i++) {
    const __nv_bfloat162 v = __hmul2(*(const __nv_bfloat162*)&e[i], (i & 1) ? __high2bfloat162(rr) : __low2bfloat162(rr));
    e[i] = *(const uint32_t*)&v;
  }
}
__host__ __device__ constexpr uint64_t qdesc(uint32_t addr) { return mkdesc(addr, 128, 256, 0); }

__global__ void __launch_bounds__(NTHREADS, 1)
fused_kernel(const Params P, const __grid_constant__ CUtensorMap mx, const __grid_constant__ CUtensorMap mw,
             const __grid_constant__ CUtensorMap mo, const __grid_constant__ CUtensorMap mu,
             const __grid_constant__ CUtensorMap mout, const __grid_constant__ CUtensorMap mw4) {
  constexpr uint32_t sb = SB;
  const int tid = threadIdx.x, lane = tid & 31;
  const int warp = __shfl_sync(0xffffffffu, tid >> 5, 0);
  const int b = blockIdx.x, oct = b >> 3, i8 = b & 7;
  const int rt = (((oct & 4) ? ~oct : oct) & 3) * 2 + (i8 >> 2);
  const int hp = (oct >> 2) * 4 + (i8 & 3);

  const int wg = warp >> 2, w = warp & 3;
  const int d = b * 4 + ((tid >> 5) & 3);
  const KgenRaw raw = kgen_load(P, d, tid >> 7, lane);
  const unsigned short dsk = __ldg((const unsigned short*)P.Dskip + d);
  if (tid < 384) {
    asm volatile("prefetch.tensormap [%0];" ::"l"(&mu) : "memory");
    asm volatile("prefetch.tensormap [%0];" ::"l"(&mw) : "memory");
    asm volatile("prefetch.tensormap [%0];" ::"l"(&mx) : "memory");
    asm volatile("prefetch.tensormap [%0];" ::"l"(&mw4) : "memory");
  }
  if (warp == 12) {
    if (lane == 0) {
#pragma unroll
      for (int i = 0; i < 9; i++) mbar_init(BAR(i), 1);
      asm volatile("fence.mbarrier_init.release.cluster;" ::: "memory");
    }
    __syncwarp();
    if (lane < 9) mbar_expect(BAR(0) + 8 * lane, (lane == 5 || lane == 7) ? 40960 : ((lane == 0 || lane > 5) ? 16384 : 28672));
    __syncwarp();
    e_tma3d(sb + OFF_W, &mw, BAR(MB_FULL), hp * 32, 0, 0);
    e_tma2d(sb + OFF_X + 3 * 16384, &mx, BAR(MB_FULL), 0, rt * 256);
    nb_arrive(NB_PROD, 192);
  } else if (warp == 14) {
    e_prefetch(P.x + (size_t)(rt * 256 + hp * 8) * 512, 8192);
  } else if (warp == 13) {
    if (lane == 0) {
#pragma unroll
      for (int i = 9; i < 39; i++) mbar_init(BAR(i), i < MB_EMPTY ? 1 : (i < MB_AUX ? 4 : 8));
      asm volatile("fence.mbarrier_init.release.cluster;" ::: "memory");
    }
    __syncwarp();
    if (lane < 13 && lane != 9) mbar_expect(BAR(MB_FULL + 8) + 8 * lane, lane < 8 ? 16384 : (lane == 8 ? 131072 : (lane == 10 ? 8192 : (lane == 11 ? 24576 : 32768))));
    nb_arrive(NB_PROD, 192);
  }
  const uint32_t tb = sb + OFF_T + w * T_CH;
  const uint32_t kp = wg >= 2 ? sb + OFF_STG0 + 16384 + w * 2048 : ((tb + 127) & ~127u) + wg * 2048;
  const KgenAddr kad = kgen_addr(lane, wg == 3 ? sb + OFF_X + 32768 + w * 2048 : kp);
  if (wg == 1) nb_sync(NB_PROD, 192);
  if (warp == 12) {
#pragma unroll 1
    for (int kb = 1; kb < 4; kb++) {
      if (kb == U_AT) e_tma4d(sb + OFF_STG0, &mu, BAR(MB_URAW), i8 * 64, oct * 2);
      e_tma3d(sb + OFF_W + kb * 12288, &mw, BAR(MB_FULL) + 8 * kb, hp * 32, kb * 64, 0);
      e_tma2d(sb + OFF_X + (kb < 2 ? kb + 3 : kb - 2) * 16384, &mx, BAR(MB_FULL) + 8 * kb, kb * 64, rt * 256);
    }
    e_tma4d(sb + OFF_W + 4 * 12288, &mw4, BAR(MB_FULL + 4), hp * 32, 4);
    e_tma4d(sb + OFF_W + 6 * 12288, &mw4, BAR(MB_FULL + 6), hp * 32, 6);
    if (smem_u32(smem_raw) != SB) __trap();
    if (lane == 0) TS1(54);
  }
  float k[5][4], k2048, ksc;
  kgen_unit(raw, kad, blockIdx.y, k, k2048, ksc);
  TS(40 + wg);
  if ((fu(k[0][0]) & fu(k[1][0]) & fu(k[2][0]) & fu(k[3][0]) & fu(k[4][0])) == 0xffffffffu) sts32(kp, 0);
  if (wg == 3) {
    nb_sync(0, 512);
    if (warp == 12) {
      asm volatile("fence.proxy.async.shared::cta;" ::: "memory");
      e_tma2d(sb + OFF_X + 2 * 16384, &mx, BAR(MB_FULL + 4), 256, rt * 256);
      if (X2_AT < 0) e_prefetch(P.x + (size_t)(rt * 256 + 128 + hp * 8) * 512, 8192);
    }
  } else if (wg) {
    nb_arrive(0, 512);
  }
  k2048 += __shfl_xor_sync(0xffffffffu, k2048, 16);
  k2048 += __shfl_xor_sync(0xffffffffu, k2048, 8);
  if (wg != 2) {
    uint32_t h[10];
#pragma unroll
    for (int j = 0; j < 10; j++) h[j] = hu(__floats2half2_rn(k[j >> 1][2 * (j & 1)], k[j >> 1][2 * (j & 1) + 1]));
    sts128(kp + lane * 16, h[0], h[1], h[2], h[3]);
    sts128(kp + 512 + lane * 16, h[4], h[5], h[6], h[7]);
    sts128(kp + 1024 + lane * 16, h[8], h[9], fu(k2048), fu(ksc));
  }
  if (wg == 0) { nb_arrive(NB_PREP, 512); nb_sync(0, 512); }
  else if (wg != 2) nb_arrive(NB_PREP, 512);
  else nb_sync(NB_PREP, 512);
  if (warp >= 12) {
    asm volatile("setmaxnreg.dec.sync.aligned.u32 32;");
    if (warp == 12) {
      uint32_t slot = sb + OFF_X + 3 * 16384;
#pragma unroll 1
      for (int n = 0; n < 11; n++) {
        mbar_spin(BAR(MB_EMPTY) + 8 * n);
        const int m = n + 5;
        e_tma2d(slot, &mx, BAR(MB_FULL) + 8 * m, (m & 7) * 64, rt * 256 + (m >> 3) * 128);
        slot = slot == sb + OFF_X + 4 * 16384 ? sb + OFF_X : slot + 16384;
        if (n == X2_AT) e_prefetch(P.x + (size_t)(rt * 256 + 128 + hp * 8) * 512, 8192);
        if (n == 7) {
          e_prefetch(P.wo + (size_t)b * 2048, 4096);
          asm volatile("prefetch.tensormap [%0];" ::"l"(&mo) : "memory");
          asm volatile("prefetch.tensormap [%0];" ::"l"(&mout) : "memory");
        }
      }
#pragma unroll 1
      for (int i = 0; i < 8; i++) {
        mbar_wait(BAR(MB_EMPTY + 10) + 8 * ((0x54332222u >> (4 * i)) & 7));
        const int w0 = (0x54736210u >> (4 * i)) & 7;
        e_tma3d(sb + OFF_W + w0 * 16384, &mo, BAR(MB_WO), 0, w0 * 64, (hp & 3) * 2);
      }
    } else {
      if (warp == 15) {
        const uint4 v0 = __ldg((const uint4*)P.wphi + hp * 64 + lane), v1 = __ldg((const uint4*)P.wphi + hp * 64 + 32 + lane);
        sts128(sb + OFF_PHI + (lane & 1) * 256 + (lane >> 1) * 16, v0.x, v0.y, v0.z, v0.w);
        sts128(sb + OFF_PHI + 512 + (lane & 1) * 256 + (lane >> 1) * 16, v1.x, v1.y, v1.z, v1.w);
        const uint32_t one = (((lane >> 3) ^ (lane >> 4)) & 1) ? 0u : ((lane & 1) ? 0x3F800000u : 0x3F80u);
        const int q = (lane >> 1) & 3;
        sts128(sb + OFF_EYE + lane * 16, q == 0 ? one : 0u, q == 1 ? one : 0u, q == 2 ? one : 0u, q == 3 ? one : 0u);
        sts64(sb + OFF_ONE + lane * 8, 0x3F803F80u, 0x3F803F80u);
        asm volatile("fence.proxy.async.shared::cta;" ::: "memory");
        nb_arrive(NB_KREAD, 160);
      }
      uint32_t* cnt = (uint32_t*)(P.xs + X_CNT) + (warp == 13 ? i8 : (warp == 14 ? 8 + rt : 16 + oct)) * 32;
      const unsigned target = (ld_x32(cnt) & ~15u) + 16;
      if (warp != 14) {
        if (warp == 15) mbar_wait(BAR(MB_EMPTY + ZERO_STEP));
        uint4* pz = P.xs + (warp == 13 ? X_PART + (hp * 8 + rt) * 144 : X_Y + b * 1024) + lane;
#pragma unroll 1
        for (int i = (warp == 13 ? 144 : 1024) - lane; i > 0; i -= 32, pz += 32) st_x(pz, 0, 0, 0, 0);
      }
      if (warp == 15) __syncwarp();
      else nb_sync(warp == 13 ? NB_INIT : NB_ODONE, warp == 13 ? 160 : 288);
      if (lane == 0) asm volatile("red.release.gpu.global.add.u32 [%0], %1;" ::"l"(cnt), "r"(warp == 15 ? 2 : 1) : "memory");
      if (lane == 0) TS1(warp == 13 ? 50 : (warp == 14 ? 57 : 53));
      asm volatile("fence.proxy.async.shared::cta;" ::: "memory");
      if (warp == 13) cnt += ((lane & 1 ? b >> 4 : i8 ^ (lane & 4)) - i8) * 32;
#pragma unroll 1
      for (int i = 0; i < SPIN_MAX; i++) {
        unsigned v;
        asm volatile("ld.acquire.gpu.global.u32 %0, [%1];" : "=r"(v) : "l"(cnt) : "memory");
        if (__all_sync(0xffffffffu, (int)(v - target) >= 0)) break;
      }
      if (lane == 0) TS1(warp == 13 ? 51 : (warp == 14 ? 58 : 55));
      if (warp == 15) { nb_arrive(NB_YZ, 160); return; }
      asm volatile("fence.proxy.async.global;" ::: "memory");
      if (warp == 13) {
        mbar_wait(BAR(MB_EMPTY + 11));
        e_expect(BAR(MB_UFULL), 4 * U_CH);
        e_bulk(sb + OFF_U, P.xs + X_UT + b * (U_CH / 4), 4 * U_CH, BAR(MB_UFULL));
      } else {
        const uint4* src = P.xs + X_O + (rt * 4 + (hp >> 2)) * 4096;
        e_bulk(sb + OFF_X + 32768 + 57344, src + 3584, 8192, BAR(MB_OA));
        e_bulk(sb + OFF_X + 32768, src, 32768, BAR(MB_OC));
        e_bulk(sb + OFF_STG0, src + 3200, 6144, BAR(MB_OB));
        nb_sync(NB_BDONE, 288);
        asm volatile("fence.proxy.async.shared::cta;" ::: "memory");
        e_bulk(sb + OFF_U, src + 2048, 18432, BAR(MB_OB));
      }
    }
    return;
  }

  const int t = tid & 127;
  const int g = lane >> 2, c = lane & 3;
  if (wg == 1) {
    mbar_wait(BAR(MB_URAW));
    TS(48);
    uint4* dst = P.xs + X_UT + (i8 * 64 + g) * (U_CH / 16) + (w & 1) * (U_ODD / 16) + U_PAD / 16 + oct * 8 + (w >> 1) * 4 + c;
    const int ln = ((lane >> 1) & 3) + 4 * (lane & 1);
    uint32_t r[8][4];
#pragma unroll
    for (int i = 0; i < 8; i++) ldsm4t(r[i], sb + OFF_STG0 + w * 4096 + ((lane >> 3) * 8 + ln) * 128 + ((i ^ ln) << 4));
#pragma unroll
    for (int i = 0; i < 8; i++) dst[i * (U_CH / 2)] = make_uint4(r[i][0], r[i][1], r[i][2], r[i][3]);
    nb_arrive(NB_INIT, 160);
    if (lane == 0) mbar_arrive(BAR(MB_AUX));
  }
  {
    if (wg == 2) {
      asm volatile("setmaxnreg.inc.sync.aligned.u32 160;");
#pragma unroll
      for (int j = 0; j < 5; j++) { k[j][0] *= ksc; k[j][1] *= ksc; k[j][2] *= ksc; k[j][3] *= ksc; }
#pragma unroll 1
      for (int q = 0; q < 3; q++) {
        const uint32_t src = (q == 2 ? kp : ((tb + 127) & ~127u) + q * 2048) + lane * 16;
        const uint4 v0 = lds128(src), v1 = lds128(src + 512), v2 = lds128(src + 1024);
        const uint32_t h[10] = {v0.x, v0.y, v0.z, v0.w, v1.x, v1.y, v1.z, v1.w, v2.x, v2.y};
#pragma unroll
        for (int j = 0; j < 10; j++) {
          const float2 f = __half22float2(*(const __half2*)&h[j]);
          k[j >> 1][2 * (j & 1)] = fmaf(f.x, uf(v2.w), k[j >> 1][2 * (j & 1)]);
          k[j >> 1][2 * (j & 1) + 1] = fmaf(f.y, uf(v2.w), k[j >> 1][2 * (j & 1) + 1]);
        }
        k2048 += uf(v2.z);
      }
#pragma unroll
      for (int o2 = 4; o2; o2 >>= 1) k2048 += __shfl_xor_sync(0xffffffffu, k2048, o2);
      if (lane == 0) k[0][0] += bf_lo(dsk);
      __syncwarp();
      if (lane == 0) mbar_arrive(BAR(MB_AUX));
      TS(34);
      build_tables(tb, lane, k, k2048);
      TS(35);
      uint4* const g_y = P.xs + X_Y;
      conv_channel(sb + OFF_U + w * U_CH, tb, lane, g_y + (size_t)d * 256 + lane);
      nb_arrive(NB_BDONE, 288);
      TS(37);
      const int lam = w * 8 + g;
      const uint4* src = g_y + (size_t)(oct * 32 + c * 8) * 256 + i8 * 32 + lam;
      uint4 v[8];
#pragma unroll 1
      for (int it = 0; it < SPIN_MAX; it++) {
        uint32_t m = 0xffffffffu;
#pragma unroll
        for (int i = 0; i < 8; i++) v[i] = ld_x(src + i * 256);
#pragma unroll
        for (int i = 0; i < 8; i++) m = min(m, v[i].x);
        if (__all_sync(0xffffffffu, m != 0)) break;
      }
      __nv_bfloat16* dst = P.out + (size_t)(i8 * 256 + (lam >> 2) * 16 + (lam & 3) * 2) * 1024 + 512 + oct * 32 + c * 8;
#pragma unroll
      for (int i = 0; i < 8; i++) *(uint4*)(dst + (size_t)((i >> 2) * 128 + ((i >> 1) & 1) * 8 + (i & 1)) * 1024) = tr_row(v, i);
      TS(38);
      GT(63);
      if (w == 0) TSDUMP(32);
      return;
    }
    if (wg == 1) {
      mbar_wait(BAR(MB_EMPTY + 4));
      mbar_spin(BAR(MB_EMPTY + 6));
    }
    TS(wg * 16 + 1);
  }

  float acc[2][48];
  {
    uint32_t fb = BAR(MB_FULL) + 64 * wg;
    uint32_t da = (uint32_t)mkdesc(sb + OFF_X, 16, 0, 0) + (wg ? 1024 : 3072), db = (uint32_t)mkdesc(sb + OFF_W, 4096, 0, 0);
    constexpr uint64_t ha = mkdesc(0, 0, 1024, 1), hb = mkdesc(0, 0, 512, 2);
    mbar_spin(fb);
    TS(wg * 16 + 2);
#pragma unroll 1
    for (int kb = 0; kb < 8; kb++) {
      WG_FENCE();
#pragma unroll
      for (int k = 0; k < 4; k++) {
        wgmma_ss_n96(acc[0], ha | (da + 2 * k), hb | (db + 64 * k), k ? 1 : kb);
        wgmma_ss_n96(acc[1], ha | (da + 2 * k + 512), hb | (db + 64 * k), k ? 1 : kb);
      }
      WG_COMMIT();
      if (kb < 7) mbar_spin(fb + 8);
      WG_WAIT(1);
      if (kb > 0) e_arrive(fb + 8 * (MB_EMPTY - MB_FULL - 1));
      fb += 8; db += 768;
      da = da == (uint32_t)mkdesc(sb + OFF_X + 65536, 16, 0, 0) ? da - 4096 : da + 1024;
    }
    if (wg == 0) nb_sync(NB_KREAD, 160);
    asm volatile("setmaxnreg.inc.sync.aligned.u32 160;");
    WG_WAIT(0);
    e_arrive(fb + 8 * (MB_EMPTY - MB_FULL - 1));
    SPLIT();
  }
  TS(wg * 16 + 3);

  constexpr uint32_t stg0 = sb + OFF_STG0, stg1 = sb + OFF_X + 32768;
  uint4* const g_part = P.xs + X_PART;
  uint4* const g_o = P.xs + X_O;
  constexpr uint32_t kvs = stg0;
  auto pack8 = [](const float* a) { return make_uint4(pack_bf(a[0], a[1]), pack_bf(a[2], a[3]), pack_bf(a[4], a[5]), pack_bf(a[6], a[7])); };
  auto feat = [&](const uint4 (&af)[4], float (&p)[4][8]) {
    WG_FENCE();
#pragma unroll
    for (int u = 0; u < 4; u++) wgmma_rs_n16(p[u], af[u], qdesc(sb + OFF_PHI + (u & 1) * 512), 0);
    WG_COMMIT();
  };
  auto packp = [](const float (&p)[4][8], uint32_t (&pw)[16]) {
#pragma unroll
    for (int i = 0; i < 16; i++) pw[i] = pack_bf(p[i >> 2][(i & 1) + 2 * (i & 2)], p[i >> 2][(i & 1) + 2 * (i & 2) + 2]);
  };
  auto contract = [&](float (&kc)[20], uint32_t stg, int acc_in) {
    WG_FENCE();
#pragma unroll
    for (int s = 0; s < 8; s++) wgmma_ss_n40(kc, qdesc(stg + s * SLAB), qdesc(stg + s * SLAB + 2048), s ? 1 : acc_in);
    WG_COMMIT();
    WG_WAIT(0);
  };
  uint32_t eq[32];
  {
    uint4 af[4], aq[4], vp[4];
    float p[4][8];
#pragma unroll
    for (int u = 0; u < 4; u++) af[u] = pack8(acc[u >> 1] + 16 + 8 * (u & 1));
    feat(af, p);
#pragma unroll
    for (int u = 0; u < 4; u++) { aq[u] = pack8(acc[u >> 1] + 8 * (u & 1)); vp[u] = pack8(acc[u >> 1] + 32 + 8 * (u & 1)); }
    WG_WAIT(0);
    uint32_t pw[16], ek[32];
    packp(p, pw);
#pragma unroll
    for (int u = 0; u < 4; u++) dual_exp(pw + 4 * u, ek + 8 * u);
    TS(wg * 16 + 12);
    mbar_spin(wg ? BAR(MB_EMPTY + 15) : BAR(MB_AUX));
    float rs[8][4];
    WG_FENCE();
#pragma unroll
    for (int i = 0; i < 8; i++) wgmma_rs_n8(rs[i], make_uint4(ek[4 * i], ek[4 * i + 1], ek[4 * i + 2], ek[4 * i + 3]), qdesc(sb + OFF_ONE), 0);
    WG_COMMIT();
    feat(aq, p);
    const uint32_t sl = (wg ? stg1 : stg0) + w * SLAB + lane * 16;
#pragma unroll
    for (int i = 0; i < 4; i++) stsm4(sl + (i >> 1) * 4 * SLAB + 2048 + (i & 1) * 512, vp[i].x, vp[i].y, vp[i].z, vp[i].w);
    sts128(sl + (lane >> 4) * (4 * SLAB - 256) + 3072, 0x3F803F80u, 0x3F803F80u, 0x3F803F80u, 0x3F803F80u);
    WG_WAIT(1);
#pragma unroll
    for (int i = 0; i < 8; i++) {
      normalise(ek + 4 * i, rs[i]);
      stsm4(sl + (i >> 2) * 4 * SLAB + (i & 3) * 512, ek[4 * i], ek[4 * i + 1], ek[4 * i + 2], ek[4 * i + 3]);
    }
    asm volatile("fence.proxy.async.shared::cta;" ::: "memory");
    TS(wg * 16 + 13);
    if (wg) {
      nb_arrive(NB_ST0, 256);
    } else {
      float kc[20];
      uint4* pp = g_part + (size_t)(hp * 8 + rt) * 144 + t;
      uint32_t* pz = (uint32_t*)(pp - t + 128) + w * 16 + c * 8 + g;
      asm volatile("" : "+l"(pp), "+l"(pz));
      nb_sync(NB_WG0, 128);
      contract(kc, stg0, 0);
      mbar_wait(BAR(MB_UFULL));
      TS(15);
      nb_sync(NB_ST0, 256);
      contract(kc, stg1, 1);
      TS(6);
      float kv[8];
#pragma unroll
      for (int i = 0; i < 8; i++) kv[i] = w & 2 ? kc[8 + i] : kc[i];
      st_x(pp, nz(pack_bf(kv[0], kv[1])), pack_bf(kv[2], kv[3]), pack_bf(kv[4], kv[5]), pack_bf(kv[6], kv[7]));
      if (c < 2) st_x32(pz, nz(fu(c ? kc[18] : kc[16])));
      TS(5);
    }
    SPLIT();
    WG_WAIT(0);
    packp(p, pw);
#pragma unroll
    for (int u = 0; u < 4; u++) dual_exp(pw + 4 * u, eq + 8 * u);
    SPLIT();
  }
  TS(wg * 16 + 4);
  if (wg == 1) {
    mbar_wait(BAR(MB_UFULL));
    const uint4* ps = g_part + (size_t)hp * 8 * 144 + t;
    const uint32_t* zs = (const uint32_t*)(g_part + (size_t)(hp * 8 + (lane >> 4) * 4) * 144 + 128) + w * 16 + (lane & 15);
    uint4 v[8];
    uint32_t zv[4];
#pragma unroll 1
    for (int it = 0; it < SPIN_MAX; it++) {
#pragma unroll
      for (int i = 0; i < 8; i++) v[i] = ld_x(ps + i * 144);
#pragma unroll
      for (int i = 0; i < 4; i++) zv[i] = ld_x32(zs + i * 576);
      uint32_t m = min(min(zv[0], zv[1]), min(zv[2], zv[3]));
#pragma unroll
      for (int i = 0; i < 8; i++) m = min(m, v[i].x);
      if (__all_sync(0xffffffffu, m != 0)) break;
    }
    float s[8];
    WG_FENCE();
#pragma unroll
    for (int r = 0; r < 8; r++) wgmma_rs_n16(s, v[r], qdesc(sb + OFF_EYE), r);
    WG_COMMIT();
    float zsum = (uf(zv[0]) + uf(zv[1])) + (uf(zv[2]) + uf(zv[3]));
    zsum += __shfl_xor_sync(0xffffffffu, zsum, 16);
    const uint32_t z1 = pack_bf(zsum, 1.f);
    if (lane < 16) sts128(kvs + w * 768 + 512 + lane * 16, z1, z1, z1, z1);
    WG_WAIT(0);
    stsm4(kvs + w * 768 + lane * 16, pack_bf(s[0], s[1]), pack_bf(s[2], s[3]), pack_bf(s[4], s[5]), pack_bf(s[6], s[7]));
    asm volatile("fence.proxy.async.shared::cta;" ::: "memory");
    TS(22);
  }
  nb_sync(NB_KV, 256);
  {
    float n[8][12];
    WG_FENCE();
#pragma unroll
    for (int i = 0; i < 8; i++) wgmma_rs_n24(n[i], make_uint4(eq[4 * i], eq[4 * i + 1], eq[4 * i + 2], eq[4 * i + 3]), qdesc(kvs + (i & 3) * 768), 0);
    WG_COMMIT();
    uint32_t* od = (uint32_t*)(g_o + (size_t)((rt * 4 + wg * 2) * 32 + hp * 2) * 128) + w * 64 + lane;
    WG_WAIT(0);
#pragma unroll
    for (int u = 0; u < 4; u++) {
      float(&np)[12] = n[2 * u];
      const float(&nm)[12] = n[2 * u + 1];
      const float q0 = np[9] * rcp(nm[9]), q1 = np[11] * rcp(nm[11]);
      const float r0 = rcp(fmaf(nm[8], q0, fmaf(np[9], 1e-6f, np[8]))), r1 = rcp(fmaf(nm[10], q1, fmaf(np[11], 1e-6f, np[10])));
#pragma unroll
      for (int i = 0; i < 8; i++) np[i] = fmaf(nm[i], (i & 2) ? q1 : q0, np[i]);
      uint32_t* o = od + (u >> 1) * 16384 + (u & 1) * 512;
      o[0] = pack_bf(np[0] * r0, np[1] * r0);
      o[32] = pack_bf(np[2] * r1, np[3] * r1);
      o[256] = pack_bf(np[4] * r0, np[5] * r0);
      o[288] = pack_bf(np[6] * r1, np[7] * r1);
      if (u == 1) SPLIT();
    }
  }
  TS(wg * 16 + 7);
  nb_arrive(NB_ODONE, 288);
  if (wg) { if (w == 0) TSDUMP(16); return; }
  mbar_wait(BAR(MB_WO));
  nb_sync(NB_BDONE, 288);
  TS(8);
  mbar_spin(BAR(MB_OA));
  TS(9);
  float oc[64];
  {
    constexpr uint64_t ha = mkdesc(0, 0, 128, 0), hb = mkdesc(0, 0, 1024, 1);
    constexpr uint32_t da0 = (uint32_t)mkdesc(stg1, 1024, 0, 0), db0 = (uint32_t)mkdesc(sb + OFF_W, 8192, 0, 0);
#pragma unroll 1
    for (int j = 0; j < 8; j++) {
      const int kb = (j + 7) & 7;
      if ((j & 3) == 1) mbar_spin(j == 1 ? BAR(MB_OC) : BAR(MB_OB));
      WG_FENCE();
#pragma unroll
      for (int k = 0; k < 4; k++) wgmma_ss_n128(oc, ha | (da0 + 512 * kb + 128 * k), hb | (db0 + 1024 * kb + 128 * k), k ? 1 : j);
      WG_COMMIT();
    }
    WG_WAIT(0);
  }
  TS(10);
  const uint32_t ot = ((sb + OFF_T + 1023) & ~1023u) + w * 4096;
#pragma unroll
  for (int hf = 0; hf < 2; hf++) {
#pragma unroll
    for (int i = 8 * hf; i < 8 * hf + 8; i += 2)
      stsm4(ot + hf * 2048 + (lane & 15) * 128 + (((i + (lane >> 4)) ^ lane) & 7) * 16, pack_bf(oc[4 * i], oc[4 * i + 1]),
            pack_bf(oc[4 * i + 2], oc[4 * i + 3]), pack_bf(oc[4 * i + 4], oc[4 * i + 5]), pack_bf(oc[4 * i + 6], oc[4 * i + 7]));
    asm volatile("fence.proxy.async.shared::cta;" ::: "memory");
    __syncwarp();
    e_store2d(&mout, ot + hf * 2048, (hp & 3) * 128 + hf * 64, (rt * 4 + (hp >> 2)) * 64 + w * 16);
  }
  asm volatile(ELECT "cp.async.bulk.commit_group;\n@p cp.async.bulk.wait_group.read 0;\n}\n" ::: "memory");
  TS(wg * 16 + 11);
  GT(61 + wg);
  if (w == 0) TSDUMP(0);
  if (w == 1) TSDUMP(48);
}

typedef CUresult (*EncodeFn)(CUtensorMap*, CUtensorMapDataType, cuuint32_t, void*, const cuuint64_t*, const cuuint64_t*,
                             const cuuint32_t*, const cuuint32_t*, CUtensorMapInterleave, CUtensorMapSwizzle,
                             CUtensorMapL2promotion, CUtensorMapFloatOOBfill);

}

extern "C" void kernel_launch(void* const* d_in, const int* in_sizes, int n_in, void* d_out, int out_size) {
  (void)in_sizes; (void)n_in; (void)out_size;
  void* fn = nullptr;
  cudaDriverEntryPointQueryResult qr;
  cudaGetDriverEntryPoint("cuTensorMapEncodeTiled", &fn, cudaEnableDefault, &qr);
  EncodeFn enc = (EncodeFn)fn;
  CUtensorMap mx, mw, mo, mu, mout, mw4;
  const cuuint32_t es[5] = {1, 1, 1, 1, 1};
  {
    cuuint64_t dims[2] = {512, 2048}, st[1] = {1024};
    cuuint32_t box[2] = {64, 128};
    enc(&mx, CU_TENSOR_MAP_DATA_TYPE_BFLOAT16, 2, d_in[0], dims, st, box, es, CU_TENSOR_MAP_INTERLEAVE_NONE,
        CU_TENSOR_MAP_SWIZZLE_128B, CU_TENSOR_MAP_L2_PROMOTION_L2_128B, CU_TENSOR_MAP_FLOAT_OOB_FILL_NONE);
  }
  {
    cuuint64_t dims[3] = {512, 512, 3}, st[2] = {3072, 1024};
    cuuint32_t box[3] = {32, 64, 3};
    enc(&mw, CU_TENSOR_MAP_DATA_TYPE_BFLOAT16, 3, d_in[1], dims, st, box, es, CU_TENSOR_MAP_INTERLEAVE_NONE,
        CU_TENSOR_MAP_SWIZZLE_64B, CU_TENSOR_MAP_L2_PROMOTION_L2_128B, CU_TENSOR_MAP_FLOAT_OOB_FILL_NONE);
  }
  {
    cuuint64_t dims[3] = {64, 512, 8}, st[2] = {1024, 128};
    cuuint32_t box[3] = {64, 64, 2};
    enc(&mo, CU_TENSOR_MAP_DATA_TYPE_BFLOAT16, 3, d_in[3], dims, st, box, es, CU_TENSOR_MAP_INTERLEAVE_NONE,
        CU_TENSOR_MAP_SWIZZLE_128B, CU_TENSOR_MAP_L2_PROMOTION_L2_128B, CU_TENSOR_MAP_FLOAT_OOB_FILL_NONE);
  }
  {
    cuuint64_t dims[4] = {512, 4, 16, 32}, st[3] = {16384, 1024, 65536};
    cuuint32_t box[4] = {64, 4, 16, 2};
    enc(&mu, CU_TENSOR_MAP_DATA_TYPE_BFLOAT16, 4, d_in[4], dims, st, box, es, CU_TENSOR_MAP_INTERLEAVE_NONE,
        CU_TENSOR_MAP_SWIZZLE_128B, CU_TENSOR_MAP_L2_PROMOTION_L2_128B, CU_TENSOR_MAP_FLOAT_OOB_FILL_NONE);
  }
  {
    cuuint64_t dims[2] = {1024, 2048}, st[1] = {2048};
    cuuint32_t box[2] = {64, 16};
    enc(&mout, CU_TENSOR_MAP_DATA_TYPE_BFLOAT16, 2, d_out, dims, st, box, es, CU_TENSOR_MAP_INTERLEAVE_NONE,
        CU_TENSOR_MAP_SWIZZLE_128B, CU_TENSOR_MAP_L2_PROMOTION_NONE, CU_TENSOR_MAP_FLOAT_OOB_FILL_NONE);
  }
  {
    cuuint64_t dims[4] = {512, 64, 3, 8}, st[3] = {3072, 1024, 64 * 3072};
    cuuint32_t box[4] = {32, 64, 3, 2};
    enc(&mw4, CU_TENSOR_MAP_DATA_TYPE_BFLOAT16, 4, d_in[1], dims, st, box, es, CU_TENSOR_MAP_INTERLEAVE_NONE,
        CU_TENSOR_MAP_SWIZZLE_64B, CU_TENSOR_MAP_L2_PROMOTION_L2_128B, CU_TENSOR_MAP_FLOAT_OOB_FILL_NONE);
  }
  Params P;
  P.x = (const __nv_bfloat16*)d_in[0];
  P.wphi = (const __nv_bfloat16*)d_in[2];
  P.wo = (const __nv_bfloat16*)d_in[3];
  P.logA = (const __nv_bfloat16*)d_in[5];
  P.Aim = (const __nv_bfloat16*)d_in[6];
  P.Cre = (const __nv_bfloat16*)d_in[7];
  P.Cim = (const __nv_bfloat16*)d_in[8];
  P.logdt = (const __nv_bfloat16*)d_in[9];
  P.Dskip = (const __nv_bfloat16*)d_in[10];
  P.out = (__nv_bfloat16*)d_out;
  cudaGetSymbolAddress((void**)&P.xs, g_x);
  P.ts = nullptr;
  cudaFuncSetAttribute(fused_kernel, cudaFuncAttributeMaxDynamicSharedMemorySize, SMEM_BYTES);
  fused_kernel<<<NCTA, NTHREADS, SMEM_BYTES>>>(P, mx, mw, mo, mu, mout, mw4);
}
```

```cpp
#include <cuda_runtime.h>
#include <cuda_bf16.h>
#include <cuda_fp16.h>
#include <cuda.h>
#include <stdint.h>

#define DBG_TS 0

namespace {

constexpr int NTHREADS = 512;
constexpr int NCTA = 128;
constexpr int OFF_W = 0;
constexpr int OFF_X = 98304;
constexpr int OFF_U = OFF_X + 65536;
constexpr int U_CH = 4416, U_ODD = 2240, U_PAD = 128;
constexpr int OFF_STG0 = OFF_U + 18432;
constexpr int SLAB = 3328;
constexpr int OFF_T = OFF_STG0 + 8 * SLAB;
constexpr int T_CH = 5216;
constexpr int T_D = 0;
constexpr int T_5 = 2144;
constexpr int T_3 = T_5 + 384;
constexpr int T_7 = T_5 + 1024;
constexpr int T_9 = T_7 + 320;
constexpr int T_KC = T_9 + 320;
constexpr int T_ST = T_5 - 1024;
constexpr int OFF_PHI = OFF_T + 4 * T_CH;
constexpr int OFF_EYE = OFF_PHI + 1024, OFF_ONE = OFF_EYE + 512;
constexpr int OFF_BAR = OFF_ONE + 256;
constexpr int SMEM_BYTES = OFF_BAR + 512 + 256 * DBG_TS;
constexpr uint32_t SB = 1024;
static_assert(T_KC + 2 * 656 <= T_CH, "table size");
static_assert(SMEM_BYTES <= 232448, "smem");
constexpr int MB_URAW = 0, MB_FULL = 1  , MB_WO = 17, MB_UFULL = 18, MB_OA = 19, MB_OB = 20, MB_OC = 21,
              MB_EMPTY = 22  , MB_AUX = 38;
__host__ __device__ constexpr uint32_t BAR(int i) { return SB + OFF_BAR + 8 * i; }
constexpr int NB_WG0 = 1, NB_ODONE = 2, NB_ST0 = 3  , NB_KV = 5, NB_YZ = 6, NB_INIT = 7, NB_PREP = 8, NB_PROD = 9, NB_KREAD = 10, NB_BDONE = 11, NB_GATE = 12,
              NB_Y = 7  ;
#define X2_AT -1
#define GATE_B 0
#define U_AT 2
#define ZERO_STEP 12
constexpr int SPIN_MAX = 1 << 16;

constexpr int X_CNT = 0;
constexpr int X_PART = 256;
constexpr int X_O = X_PART + 16 * 8 * 144;
constexpr int X_Y = X_O + 32 * 32 * 128;
constexpr int X_UT = X_Y + 512 * 8 * 32;
constexpr int X_SIZE = X_UT + 512 * (U_CH / 16);
__device__ __align__(128) uint4 g_x[X_SIZE];
extern __shared__ uint8_t smem_raw[];
#define TS(i) do {} while (0)
#define TS1(i) do {} while (0)
#define GT(i) do {} while (0)
#define TSDUMP(base) do {} while (0)

__device__ __forceinline__ uint32_t smem_u32(const void* p) { return (uint32_t)__cvta_generic_to_shared(p); }
__device__ __forceinline__ void mbar_arrive(uint32_t b) {
  asm volatile("mbarrier.arrive.shared::cta.b64 _, [%0];" ::"r"(b) : "memory");
}
__device__ __forceinline__ void mbar_wait(uint32_t b) {
  uint32_t done = 0;
#pragma unroll 1
  for (int i = 0; i < SPIN_MAX && !done; i++) {
    asm volatile("{\n.reg .pred p;\nmbarrier.try_wait.parity.shared::cta.b64 p, [%1], 0, 4000;\nselp.u32 %0, 1, 0, p;\n}\n"
                 : "=r"(done) : "r"(b) : "memory");
  }
}
__device__ __forceinline__ void mbar_spin(uint32_t b) {
  uint32_t done = 0;
#pragma unroll 1
  for (int i = 0; i < (SPIN_MAX << 4) && !done; i++) {
    asm volatile("{\n.reg .pred p;\nmbarrier.try_wait.parity.shared::cta.b64 p, [%1], 0;\nselp.u32 %0, 1, 0, p;\n}\n"
                 : "=r"(done) : "r"(b) : "memory");
  }
}
__device__ __forceinline__ void mbar_init(uint32_t b, int n) {
  asm volatile("mbarrier.init.shared::cta.b64 [%0], %1;" ::"r"(b), "r"(n) : "memory");
}
__device__ __forceinline__ void mbar_expect(uint32_t b, int bytes) {
  asm volatile("mbarrier.arrive.expect_tx.shared::cta.b64 _, [%0], %1;" ::"r"(b), "r"(bytes) : "memory");
}
__device__ __forceinline__ void nb_sync(int id, int n) { asm volatile("bar.sync %0, %1;" ::"r"(id), "r"(n) : "memory"); }
__device__ __forceinline__ void nb_arrive(int id, int n) { asm volatile("bar.arrive %0, %1;" ::"r"(id), "r"(n) : "memory"); }
#define ELECT "{\n.reg .pred p;\nelect.sync _|p, 0xffffffff;\n@p "
__device__ __forceinline__ void e_arrive(uint32_t b) {
  asm volatile(ELECT "mbarrier.arrive.shared::cta.b64 _, [%0];\n}\n" ::"r"(b) : "memory");
}
__device__ __forceinline__ void e_expect(uint32_t b, int bytes) {
  asm volatile(ELECT "mbarrier.arrive.expect_tx.shared::cta.b64 _, [%0], %1;\n}\n" ::"r"(b), "r"(bytes) : "memory");
}
__device__ __forceinline__ void e_tma2d(uint32_t dst, const CUtensorMap* m, uint32_t bar, int c0, int c1) {
  asm volatile(ELECT "cp.async.bulk.tensor.2d.shared::cluster.global.mbarrier::complete_tx::bytes [%0], [%1, {%3,%4}], [%2];\n}\n"
               ::"r"(dst), "l"(m), "r"(bar), "r"(c0), "r"(c1) : "memory");
}
__device__ __forceinline__ void e_tma3d(uint32_t dst, const CUtensorMap* m, uint32_t bar, int c0, int c1, int c2) {
  asm volatile(ELECT "cp.async.bulk.tensor.3d.shared::cluster.global.mbarrier::complete_tx::bytes [%0], [%1, {%3,%4,%5}], [%2];\n}\n"
               ::"r"(dst), "l"(m), "r"(bar), "r"(c0), "r"(c1), "r"(c2) : "memory");
}
__device__ __forceinline__ void e_tma4d(uint32_t dst, const CUtensorMap* m, uint32_t bar, int c0, int c3) {
  asm volatile(ELECT "cp.async.bulk.tensor.4d.shared::cluster.global.mbarrier::complete_tx::bytes [%0], [%1, {%3,%5,%5,%4}], [%2];\n}\n"
               ::"r"(dst), "l"(m), "r"(bar), "r"(c0), "r"(c3), "r"(0) : "memory");
}
__device__ __forceinline__ void e_bulk(uint32_t dst, const void* src, int bytes, uint32_t bar) {
  asm volatile(ELECT "cp.async.bulk.shared::cluster.global.mbarrier::complete_tx::bytes [%0], [%1], %2, [%3];\n}\n"
               ::"r"(dst), "l"(src), "r"(bytes), "r"(bar) : "memory");
}
__device__ __forceinline__ void e_prefetch(const void* p, int bytes) {
  asm volatile(ELECT "cp.async.bulk.prefetch.L2.global [%0], %1;\n}\n" ::"l"(p), "r"(bytes) : "memory");
}
__device__ __forceinline__ void e_store2d(const CUtensorMap* m, uint32_t src, int c0, int c1) {
  asm volatile(ELECT "cp.async.bulk.tensor.2d.global.shared::cta.bulk_group [%0, {%2,%3}], [%1];\n}\n"
               ::"l"(m), "r"(src), "r"(c0), "r"(c1) : "memory");
}
__host__ __device__ constexpr uint64_t mkdesc(uint32_t addr, uint32_t lbo, uint32_t sbo, int swz) {
  return (uint64_t)((addr & 0x3FFFF) >> 4) | ((uint64_t)(lbo >> 4) << 16) | ((uint64_t)(sbo >> 4) << 32) |
         ((uint64_t)swz << 62);
}
#define SPLIT() asm volatile("{\n.reg .pred p;\nsetp.eq.u32 p, %0, %1;\n@p exit;\n}\n" ::"r"(blockIdx.y), "n"(__LINE__) : "memory")
#define WG_FENCE() asm volatile("wgmma.fence.sync.aligned;" ::: "memory")
#define WG_COMMIT() asm volatile("wgmma.commit_group.sync.aligned;" ::: "memory")
#define WG_WAIT(n) asm volatile("wgmma.wait_group.sync.aligned " #n ";" ::: "memory")

__device__ __forceinline__ void mma(float& d0, float& d1, float& d2, float& d3, uint32_t a0, uint32_t a1, uint32_t a2,
                                    uint32_t a3, uint32_t b0, uint32_t b1) {
  asm volatile("mma.sync.aligned.m16n8k16.row.col.f32.bf16.bf16.f32 {%0,%1,%2,%3},{%4,%5,%6,%7},{%8,%9},{%0,%1,%2,%3};"
               : "+f"(d0), "+f"(d1), "+f"(d2), "+f"(d3)
               : "r"(a0), "r"(a1), "r"(a2), "r"(a3), "r"(b0), "r"(b1));
}
__device__ __forceinline__ void mmac(float (&d)[4], uint32_t a0, uint32_t a1, uint32_t a2, uint32_t a3, uint32_t b0,
                                     uint32_t b1, const float (&c)[4]) {
  asm volatile("mma.sync.aligned.m16n8k16.row.col.f32.bf16.bf16.f32 {%0,%1,%2,%3},{%4,%5,%6,%7},{%8,%9},{%10,%11,%12,%13};"
               : "=f"(d[0]), "=f"(d[1]), "=f"(d[2]), "=f"(d[3])
               : "r"(a0), "r"(a1), "r"(a2), "r"(a3), "r"(b0), "r"(b1), "f"(c[0]), "f"(c[1]), "f"(c[2]), "f"(c[3]));
}
__device__ __forceinline__ void mma_p(int p, float (&d)[4], uint32_t a0, uint32_t a1, uint32_t a2, uint32_t a3, uint32_t b0, uint32_t b1) {
  asm volatile("{\n.reg .pred q;\nsetp.ne.b32 q, %10, 0;\n"
               "@q mma.sync.aligned.m16n8k16.row.col.f32.bf16.bf16.f32 {%0,%1,%2,%3},{%4,%5,%6,%7},{%8,%9},{%0,%1,%2,%3};\n}\n"
               : "+f"(d[0]), "+f"(d[1]), "+f"(d[2]), "+f"(d[3])
               : "r"(a0), "r"(a1), "r"(a2), "r"(a3), "r"(b0), "r"(b1), "r"(p));
}
__device__ __forceinline__ void mmac_p(int p, float (&d)[4], uint32_t a0, uint32_t a1, uint32_t a2, uint32_t a3, uint32_t b0,
                                       uint32_t b1, const float (&c)[4]) {
  asm volatile("{\n.reg .pred q;\nsetp.ne.b32 q, %14, 0;\n"
               "@q mma.sync.aligned.m16n8k16.row.col.f32.bf16.bf16.f32 {%0,%1,%2,%3},{%4,%5,%6,%7},{%8,%9},{%10,%11,%12,%13};\n}\n"
               : "+f"(d[0]), "+f"(d[1]), "+f"(d[2]), "+f"(d[3])
               : "r"(a0), "r"(a1), "r"(a2), "r"(a3), "r"(b0), "r"(b1), "f"(c[0]), "f"(c[1]), "f"(c[2]), "f"(c[3]), "r"(p));
}
__device__ __forceinline__ void mma_h(float (&d)[4], const uint32_t (&a)[4], uint32_t b0, uint32_t b1) {
  asm volatile("mma.sync.aligned.m16n8k16.row.col.f32.f16.f16.f32 {%0,%1,%2,%3},{%4,%5,%6,%7},{%8,%9},{%0,%1,%2,%3};"
               : "+f"(d[0]), "+f"(d[1]), "+f"(d[2]), "+f"(d[3]) : "r"(a[0]), "r"(a[1]), "r"(a[2]), "r"(a[3]), "r"(b0), "r"(b1));
}
__device__ __forceinline__ void mma0(float& d0, float& d1, float& d2, float& d3, uint32_t a0, uint32_t a1, uint32_t a2,
                                     uint32_t a3, uint32_t b0, uint32_t b1) {
  asm volatile("mma.sync.aligned.m16n8k16.row.col.f32.bf16.bf16.f32 {%0,%1,%2,%3},{%4,%5,%6,%7},{%8,%9},{%10,%10,%10,%10};"
               : "=f"(d0), "=f"(d1), "=f"(d2), "=f"(d3)
               : "r"(a0), "r"(a1), "r"(a2), "r"(a3), "r"(b0), "r"(b1), "f"(0.f));
}
__device__ __forceinline__ uint32_t pack_bf(float lo, float hi) {
  uint32_t r;
  asm("cvt.rn.bf16x2.f32 %0, %1, %2;" : "=r"(r) : "f"(hi), "f"(lo));
  return r;
}
__device__ __forceinline__ float bf_lo(uint32_t w) { return __uint_as_float(w << 16); }
__device__ __forceinline__ float bf_hi(uint32_t w) { return __uint_as_float(w & 0xffff0000u); }
__device__ __forceinline__ float bf_round(float x) { return __bfloat162float(__float2bfloat16_rn(x)); }
__device__ __forceinline__ uint32_t bmax2(uint32_t a, uint32_t b) {
  uint32_t r; asm("max.bf16x2 %0, %1, %2;" : "=r"(r) : "r"(a), "r"(b)); return r;
}
__device__ __forceinline__ uint32_t bmin2(uint32_t a, uint32_t b) {
  uint32_t r; asm("min.bf16x2 %0, %1, %2;" : "=r"(r) : "r"(a), "r"(b)); return r;
}
__device__ __forceinline__ float ex2(float x) { float r; asm("ex2.approx.ftz.f32 %0, %1;" : "=f"(r) : "f"(x)); return r; }
__device__ __forceinline__ float rcp(float x) { float r; asm("rcp.approx.ftz.f32 %0, %1;" : "=f"(r) : "f"(x)); return r; }
__device__ __forceinline__ void ldsm4(uint32_t (&r)[4], uint32_t a) {
  asm volatile("ldmatrix.sync.aligned.m8n8.x4.shared.b16 {%0,%1,%2,%3}, [%4];"
               : "=r"(r[0]), "=r"(r[1]), "=r"(r[2]), "=r"(r[3]) : "r"(a) : "memory");
}
__device__ __forceinline__ void ldsm4t(uint32_t (&r)[4], uint32_t a) {
  asm volatile("ldmatrix.sync.aligned.m8n8.x4.trans.shared.b16 {%0,%1,%2,%3}, [%4];"
               : "=r"(r[0]), "=r"(r[1]), "=r"(r[2]), "=r"(r[3]) : "r"(a) : "memory");
}
__device__ __forceinline__ void stsm4(uint32_t a, uint32_t r0, uint32_t r1, uint32_t r2, uint32_t r3) {
  asm volatile("stmatrix.sync.aligned.m8n8.x4.shared.b16 [%0], {%1,%2,%3,%4};"
               ::"r"(a), "r"(r0), "r"(r1), "r"(r2), "r"(r3) : "memory");
}
__device__ __forceinline__ uint32_t lds32(uint32_t a) {
  uint32_t r; asm volatile("ld.shared.u32 %0, [%1];" : "=r"(r) : "r"(a) : "memory"); return r;
}
__device__ __forceinline__ uint32_t lds16(uint32_t a) {
  uint32_t r; asm volatile("{\n.reg .u16 h;\nld.shared.u16 h, [%1];\ncvt.u32.u16 %0, h;\n}\n" : "=r"(r) : "r"(a) : "memory"); return r;
}
__device__ __forceinline__ uint2 lds64(uint32_t a) {
  uint2 r; asm volatile("ld.shared.v2.u32 {%0,%1}, [%2];" : "=r"(r.x), "=r"(r.y) : "r"(a) : "memory"); return r;
}
__device__ __forceinline__ uint4 lds128(uint32_t a) {
  uint4 r;
  asm volatile("ld.shared.v4.u32 {%0,%1,%2,%3}, [%4];" : "=r"(r.x), "=r"(r.y), "=r"(r.z), "=r"(r.w) : "r"(a) : "memory");
  return r;
}
__device__ __forceinline__ void sts32(uint32_t a, uint32_t v) { asm volatile("st.shared.u32 [%0], %1;" ::"r"(a), "r"(v) : "memory"); }
__device__ __forceinline__ void sts16(uint32_t a, uint32_t v) {
  asm volatile("{\n.reg .u16 h;\ncvt.u16.u32 h, %1;\nst.shared.u16 [%0], h;\n}\n" ::"r"(a), "r"(v) : "memory");
}
__device__ __forceinline__ void sts64(uint32_t a, uint32_t x, uint32_t y) {
  asm volatile("st.shared.v2.u32 [%0], {%1,%2};" ::"r"(a), "r"(x), "r"(y) : "memory");
}
__device__ __forceinline__ void sts128(uint32_t a, uint32_t x, uint32_t y, uint32_t z, uint32_t w) {
  asm volatile("st.shared.v4.u32 [%0], {%1,%2,%3,%4};" ::"r"(a), "r"(x), "r"(y), "r"(z), "r"(w) : "memory");
}
__device__ __forceinline__ uint4 ld_x(const uint4* p) {
  uint4 r;
  asm volatile("{\n.reg .b128 t;\nld.relaxed.gpu.global.b128 t, [%4];\nmov.b128 {%0,%1,%2,%3}, t;\n}\n"
               : "=r"(r.x), "=r"(r.y), "=r"(r.z), "=r"(r.w) : "l"(p) : "memory");
  return r;
}
__device__ __forceinline__ uint32_t ld_x32(const uint32_t* p) {
  uint32_t r; asm volatile("ld.relaxed.gpu.global.u32 %0, [%1];" : "=r"(r) : "l"(p) : "memory"); return r;
}
__device__ __forceinline__ void st_x(uint4* p, uint32_t x, uint32_t y, uint32_t z, uint32_t w) {
  asm volatile("{\n.reg .b128 t;\nmov.b128 t, {%1,%2,%3,%4};\nst.relaxed.gpu.global.b128 [%0], t;\n}\n"
               ::"l"(p), "r"(x), "r"(y), "r"(z), "r"(w) : "memory");
}
__device__ __forceinline__ void st_x_p(int p, uint4* a, uint32_t x, uint32_t y, uint32_t z, uint32_t w) {
  asm volatile("{\n.reg .b128 t;\n.reg .pred q;\nsetp.ne.b32 q, %5, 0;\nmov.b128 t, {%1,%2,%3,%4};\n@q st.relaxed.gpu.global.b128 [%0], t;\n}\n"
               ::"l"(a), "r"(x), "r"(y), "r"(z), "r"(w), "r"(p) : "memory");
}
__device__ __forceinline__ void sts64_p(int p, uint32_t a, uint32_t x, uint32_t y) {
  asm volatile("{\n.reg .pred q;\nsetp.ne.b32 q, %3, 0;\n@q st.shared.v2.u32 [%0], {%1,%2};\n}\n" ::"r"(a), "r"(x), "r"(y), "r"(p) : "memory");
}
__device__ __forceinline__ void st_x32(uint32_t* p, uint32_t x) {
  asm volatile("st.relaxed.gpu.global.u32 [%0], %1;" ::"l"(p), "r"(x) : "memory");
}
__device__ __forceinline__ uint32_t nz(uint32_t w) { return max(w, 1u); }
__device__ __forceinline__ uint32_t fu(float x) { return __float_as_uint(x); }
__device__ __forceinline__ float uf(uint32_t x) { return __uint_as_float(x); }

__device__ __forceinline__ void wgmma_ss_n96(float (&d)[48], uint64_t da, uint64_t db, int sc) {
  asm volatile("{\n.reg .pred p;\nsetp.ne.b32 p, %50, 0;\n"
      "wgmma.mma_async.sync.aligned.m64n96k16.f32.bf16.bf16 "
      "{%0,%1,%2,%3,%4,%5,%6,%7,%8,%9,%10,%11,%12,%13,%14,%15,%16,%17,%18,%19,%20,%21,%22,%23,%24,%25,%26,%27,%28,%29,%30,%31,%32,%33,%34,%35,%36,%37,%38,%39,%40,%41,%42,%43,%44,%45,%46,%47}, "
      "%48, %49, p, 1, 1, 0, 1;\n}\n"
      : "+f"(d[0]), "+f"(d[1]), "+f"(d[2]), "+f"(d[3]), "+f"(d[4]), "+f"(d[5]), "+f"(d[6]), "+f"(d[7]),
        "+f"(d[8]), "+f"(d[9]), "+f"(d[10]), "+f"(d[11]), "+f"(d[12]), "+f"(d[13]), "+f"(d[14]), "+f"(d[15]),
        "+f"(d[16]), "+f"(d[17]), "+f"(d[18]), "+f"(d[19]), "+f"(d[20]), "+f"(d[21]), "+f"(d[22]), "+f"(d[23]),
        "+f"(d[24]), "+f"(d[25]), "+f"(d[26]), "+f"(d[27]), "+f"(d[28]), "+f"(d[29]), "+f"(d[30]), "+f"(d[31]),
        "+f"(d[32]), "+f"(d[33]), "+f"(d[34]), "+f"(d[35]), "+f"(d[36]), "+f"(d[37]), "+f"(d[38]), "+f"(d[39]),
        "+f"(d[40]), "+f"(d[41]), "+f"(d[42]), "+f"(d[43]), "+f"(d[44]), "+f"(d[45]), "+f"(d[46]), "+f"(d[47])
      : "l"(da), "l"(db), "r"(sc));
}

__device__ __forceinline__ void wgmma_ss_n128(float (&d)[64], uint64_t da, uint64_t db, int sc) {
  asm volatile("{\n.reg .pred p;\nsetp.ne.b32 p, %66, 0;\n"
      "wgmma.mma_async.sync.aligned.m64n128k16.f32.bf16.bf16 "
      "{%0,%1,%2,%3,%4,%5,%6,%7,%8,%9,%10,%11,%12,%13,%14,%15,%16,%17,%18,%19,%20,%21,%22,%23,%24,%25,%26,%27,%28,%29,%30,%31,%32,%33,%34,%35,%36,%37,%38,%39,%40,%41,%42,%43,%44,%45,%46,%47,%48,%49,%50,%51,%52,%53,%54,%55,%56,%57,%58,%59,%60,%61,%62,%63}, "
      "%64, %65, p, 1, 1, 0, 1;\n}\n"
      : "+f"(d[0]), "+f"(d[1]), "+f"(d[2]), "+f"(d[3]), "+f"(d[4]), "+f"(d[5]), "+f"(d[6]), "+f"(d[7]),
        "+f"(d[8]), "+f"(d[9]), "+f"(d[10]), "+f"(d[11]), "+f"(d[12]), "+f"(d[13]), "+f"(d[14]), "+f"(d[15]),
        "+f"(d[16]), "+f"(d[17]), "+f"(d[18]), "+f"(d[19]), "+f"(d[20]), "+f"(d[21]), "+f"(d[22]), "+f"(d[23]),
        "+f"(d[24]), "+f"(d[25]), "+f"(d[26]), "+f"(d[27]), "+f"(d[28]), "+f"(d[29]), "+f"(d[30]), "+f"(d[31]),
        "+f"(d[32]), "+f"(d[33]), "+f"(d[34]), "+f"(d[35]), "+f"(d[36]), "+f"(d[37]), "+f"(d[38]), "+f"(d[39]),
        "+f"(d[40]), "+f"(d[41]), "+f"(d[42]), "+f"(d[43]), "+f"(d[44]), "+f"(d[45]), "+f"(d[46]), "+f"(d[47]),
        "+f"(d[48]), "+f"(d[49]), "+f"(d[50]), "+f"(d[51]), "+f"(d[52]), "+f"(d[53]), "+f"(d[54]), "+f"(d[55]),
        "+f"(d[56]), "+f"(d[57]), "+f"(d[58]), "+f"(d[59]), "+f"(d[60]), "+f"(d[61]), "+f"(d[62]), "+f"(d[63])
      : "l"(da), "l"(db), "r"(sc));
}

__device__ __forceinline__ void wgmma_ss_n40(float (&d)[20], uint64_t da, uint64_t db, int sc) {
  asm volatile("{\n.reg .pred p;\nsetp.ne.b32 p, %22, 0;\n"
      "wgmma.mma_async.sync.aligned.m64n40k16.f32.bf16.bf16 "
      "{%0,%1,%2,%3,%4,%5,%6,%7,%8,%9,%10,%11,%12,%13,%14,%15,%16,%17,%18,%19}, "
      "%20, %21, p, 1, 1, 1, 1;\n}\n"
      : "+f"(d[0]), "+f"(d[1]), "+f"(d[2]), "+f"(d[3]), "+f"(d[4]), "+f"(d[5]), "+f"(d[6]), "+f"(d[7]),
        "+f"(d[8]), "+f"(d[9]), "+f"(d[10]), "+f"(d[11]), "+f"(d[12]), "+f"(d[13]), "+f"(d[14]), "+f"(d[15]),
        "+f"(d[16]), "+f"(d[17]), "+f"(d[18]), "+f"(d[19])
      : "l"(da), "l"(db), "r"(sc));
}

__device__ __forceinline__ void wgmma_rs_n8(float (&d)[4], const uint4& a, uint64_t db, int sc) {
  asm volatile("{\n.reg .pred p;\nsetp.ne.b32 p, %9, 0;\n"
      "wgmma.mma_async.sync.aligned.m64n8k16.f32.bf16.bf16 "
      "{%0,%1,%2,%3}, "
      "{%4,%5,%6,%7}, %8, p, 1, 1, 1;\n}\n"
      : "+f"(d[0]), "+f"(d[1]), "+f"(d[2]), "+f"(d[3])
      : "r"(a.x), "r"(a.y), "r"(a.z), "r"(a.w), "l"(db), "r"(sc));
}

__device__ __forceinline__ void wgmma_rs_n16(float (&d)[8], const uint4& a, uint64_t db, int sc) {
  asm volatile("{\n.reg .pred p;\nsetp.ne.b32 p, %13, 0;\n"
      "wgmma.mma_async.sync.aligned.m64n16k16.f32.bf16.bf16 "
      "{%0,%1,%2,%3,%4,%5,%6,%7}, "
      "{%8,%9,%10,%11}, %12, p, 1, 1, 1;\n}\n"
      : "+f"(d[0]), "+f"(d[1]), "+f"(d[2]), "+f"(d[3]), "+f"(d[4]), "+f"(d[5]), "+f"(d[6]), "+f"(d[7])
      : "r"(a.x), "r"(a.y), "r"(a.z), "r"(a.w), "l"(db), "r"(sc));
}

__device__ __forceinline__ void wgmma_rs_n24(float (&d)[12], const uint4& a, uint64_t db, int sc) {
  asm volatile("{\n.reg .pred p;\nsetp.ne.b32 p, %17, 0;\n"
      "wgmma.mma_async.sync.aligned.m64n24k16.f32.bf16.bf16 "
      "{%0,%1,%2,%3,%4,%5,%6,%7,%8,%9,%10,%11}, "
      "{%12,%13,%14,%15}, %16, p, 1, 1, 1;\n}\n"
      : "+f"(d[0]), "+f"(d[1]), "+f"(d[2]), "+f"(d[3]), "+f"(d[4]), "+f"(d[5]), "+f"(d[6]), "+f"(d[7]),
        "+f"(d[8]), "+f"(d[9]), "+f"(d[10]), "+f"(d[11])
      : "r"(a.x), "r"(a.y), "r"(a.z), "r"(a.w), "l"(db), "r"(sc));
}

struct Params {
  const __nv_bfloat16 *logA, *Aim, *Cre, *Cim, *logdt, *Dskip, *x, *wphi, *wo;
  __nv_bfloat16* out;
  uint4* xs;
  long long* ts;
};

__device__ __forceinline__ uint4 tr_row(const uint4 (&v)[8], int i) {
  uint32_t o[4];
#pragma unroll
  for (int m = 0; m < 4; m++) {
    const uint4 &ra = v[2 * m], &rb = v[2 * m + 1];
    const int k = i >> 1;
    const uint32_t xa = k == 0 ? ra.x : k == 1 ? ra.y : k == 2 ? ra.z : ra.w;
    const uint32_t xb = k == 0 ? rb.x : k == 1 ? rb.y : k == 2 ? rb.z : rb.w;
    o[m] = __byte_perm(xa, xb, (i & 1) ? 0x7632 : 0x5410);
  }
  return make_uint4(o[0], o[1], o[2], o[3]);
}

struct cpx { float r, i; };
__device__ __forceinline__ cpx csq(cpx a) { return {a.r * a.r - a.i * a.i, 2.f * (a.r * a.i)}; }
__device__ __forceinline__ cpx polar(float e, float t) {
  const float m = ex2(e);
  return {m * __cosf(t), m * __sinf(t)};
}

struct KgenRaw { unsigned short la, ai, cr, ci, ldt; };
__device__ __forceinline__ KgenRaw kgen_load(const Params& P, int d, int unit, int lane) {
  const int o = d * 128 + unit * 32 + lane;
  return {__ldg((const unsigned short*)P.logA + o), __ldg((const unsigned short*)P.Aim + o), __ldg((const unsigned short*)P.Cre + o),
          __ldg((const unsigned short*)P.Cim + o), __ldg((const unsigned short*)P.logdt + d)};
}
struct hmul { __half2 a, b; };
__device__ __forceinline__ hmul mk_mul(cpx w) {
  uint32_t b;
  asm("{\n.reg .f32 n;\nneg.ftz.f32 n, %1;\ncvt.rn.f16x2.f32 %0, %2, n;\n}\n" : "=r"(b) : "f"(w.i), "f"(w.r));
  return {__floats2half2_rn(w.r, w.i), *(const __half2*)&b};
}
__device__ __forceinline__ __half2 hcm(__half2 z, const hmul& w) { return __hfma2(__high2half2(z), w.b, __hmul2(__low2half2(z), w.a)); }
__device__ __forceinline__ uint32_t hu(__half2 v) { return *(const uint32_t*)&v; }

struct KgenAddr { uint32_t sa, sb, lb, lc, la; };
__device__ __forceinline__ KgenAddr kgen_addr(int lane, uint32_t buf) {
  KgenAddr a;
  a.sa = buf + (lane & 7) * 128 + ((((lane >> 3) ^ lane) & 7) << 4);
  a.lb = buf + (lane >> 3) * 128 + (((lane ^ (lane >> 3)) & 7) << 4);
  a.la = buf + ((lane >> 3) & 1) * 1024 + (lane >> 4) * 128 + (((lane ^ (lane >> 4)) & 7) << 4);
  a.sb = a.sa ^ 64; a.lc = a.lb ^ 64;
  asm volatile("" : "+r"(a.sa), "+r"(a.sb), "+r"(a.lb), "+r"(a.lc), "+r"(a.la));
  return a;
}
__device__ __forceinline__ void kgen_unit(const KgenRaw& r, const KgenAddr& ad, uint32_t zero, float (&k)[5][4], float& k2048, float& sc) {
  const float dt = bf_round(expf(bf_lo(r.ldt)));
  const float a2 = bf_round(ex2(bf_lo(r.la) * 1.4426950408889634f)) * (dt * -1.4426950408889634f);
  const float f = bf_lo(r.ai) * dt;
  const float r128 = f * 20.371832715762604f;
  const uint32_t ex = min(max(__reduce_max_sync(0xffffffffu, max(r.cr & 0x7fffu, r.ci & 0x7fffu)) >> 7, 1u), 253u);
  const float cs = uf((254u - ex) << 23);
  sc = 2.f * dt * uf(ex << 23);
  const cpx C = {bf_lo(r.cr) * cs, -bf_lo(r.ci) * cs};
  auto put = [&](const __half2 (&v)[8], uint32_t off) {
    stsm4(ad.sa + off, hu(v[0]), hu(v[1]), hu(v[2]), hu(v[3]));
    stsm4(ad.sb + off, hu(v[4]), hu(v[5]), hu(v[6]), hu(v[7]));
  };
  uint32_t A[4][4], B[5][2][4];
  auto get = [&](int j, uint32_t off) {
    __syncwarp();
    ldsm4(B[j][0], ad.lb + off);
    ldsm4(B[j][1], ad.lc + 512 + off);
  };
  auto tile = [&](int j) {
    k[j][0] = k[j][1] = k[j][2] = k[j][3] = 0.f;
#pragma unroll
    for (int s = 0; s < 4; s++) mma_h(k[j], A[s], B[j][s >> 1][2 * (s & 1)], B[j][s >> 1][2 * (s & 1) + 1]);
  };
  auto after = [&](cpx v, uint32_t dep) { return cpx{uf(fu(v.r) ^ (dep & zero)), v.i}; };
  const cpx w1 = polar(a2, f), w128 = polar(a2 * 128.f, (r128 - rintf(r128)) * 6.283185307179586f);
  const cpx w2 = csq(w1), w4 = csq(w2);
  __half2 t0[8], t1[8], t2[8], t3[8], t4[8];
  const hmul m2 = mk_mul(w2), m4 = mk_mul(w4), m128 = mk_mul(w128);
  t0[0] = __floats2half2_rn(1.f, 0.f); t0[1] = __floats2half2_rn(w1.r, w1.i); t0[2] = m2.a; t0[4] = m4.a;
  t0[3] = hcm(t0[1], m2); t0[5] = hcm(t0[1], m4); t0[6] = hcm(t0[2], m4); t0[7] = hcm(t0[3], m4);
  put(t0, 0); get(0, 0);
  t1[0] = m128.a;
#pragma unroll
  for (int i = 1; i < 8; i++) t1[i] = hcm(t0[i], m128);
  put(t1, 1024); get(1, 1024);
  {
    cpx w8 = csq(after(w4, B[0][0][0]));
    w8.i = -w8.i;
    const cpx w16 = csq(w8), w32 = csq(w16), w64 = csq(w32);
    const hmul m8 = mk_mul(w8), m16 = mk_mul(w16), m32 = mk_mul(w32), m64 = mk_mul(w64);
    __half2 a[8];
    a[0] = __floats2half2_rn(C.r, C.i); a[1] = hcm(a[0], m8);
    a[2] = hcm(a[0], m16); a[3] = hcm(a[1], m16);
#pragma unroll
    for (int i = 0; i < 4; i++) a[4 + i] = hcm(a[i], m32);
    put(a, 0);
#pragma unroll
    for (int i = 0; i < 8; i++) a[i] = hcm(a[i], m64);
    put(a, 1024);
    __syncwarp();
#pragma unroll
    for (int s = 0; s < 4; s++) ldsm4(A[s], (ad.la ^ (s << 5)) + s * 256);
  }
  const cpx w256 = csq(after(w128, B[1][0][0]));
  const hmul m256 = mk_mul(w256);
  t2[0] = m256.a;
#pragma unroll
  for (int i = 1; i < 8; i++) t2[i] = hcm((i & 1) ? t1[i & 6] : t0[i & 6], m256);
  put(t2, 0); get(2, 0);
  tile(0); tile(1);
  const cpx w512 = csq(after(w256, A[0][0]));
  const hmul m512 = mk_mul(w512);
  t3[0] = m512.a;
#pragma unroll
  for (int i = 1; i < 8; i++) t3[i] = hcm((i & 2) ? t2[i & 5] : ((i & 1) ? t1[i & 4] : t0[i & 4]), m512);
  put(t3, 1024); get(3, 1024);
  tile(2);
  const cpx w1024 = csq(after(w512, B[2][0][0])), we = csq(w1024);
  const hmul m1024 = mk_mul(w1024);
  t4[0] = m1024.a;
#pragma unroll
  for (int i = 1; i < 8; i++) t4[i] = hcm((i & 4) ? t3[i & 3] : ((i & 2) ? t2[i & 1] : t1[0]), m1024);
  put(t4, 0); get(4, 0);
  tile(3); tile(4);
  k2048 = (C.r * we.r + C.i * we.i) * sc;
}

__device__ __forceinline__ void build_tables(uint32_t tb, int lane, float (&k)[5][4], float k2048) {
  const int g = lane >> 2, c = lane & 3;
  const uint32_t kc = tb + T_KC + 16;
  {
    const uint32_t a0 = kc + 16 * g + 4 * c, a2 = kc + 2 * (256 + 4 * g + c);
    const uint32_t a3 = kc + 2 * (384 + 2 * g + 64 * (c & 1) + (c >> 1)), a4 = kc + 2 * (512 + g + 32 * c);
#pragma unroll
    for (int r = 0; r < 2; r++) {
      sts32(a0 + 128 * r, pack_bf(k[0][2 * r], k[0][2 * r + 1]));
      sts32(a0 + 128 * r + 256, pack_bf(k[1][2 * r], k[1][2 * r + 1]));
      const uint32_t w2 = pack_bf(k[2][2 * r], k[2][2 * r + 1]);
      const uint32_t w3 = pack_bf(k[3][2 * r], k[3][2 * r + 1]);
      const uint32_t w4 = pack_bf(k[4][2 * r], k[4][2 * r + 1]);
      sts16(a2 + 64 * r, w2); sts16(a2 + 64 * r + 128, w2 >> 16);
      sts16(a3 + 32 * r, w3); sts16(a3 + 32 * r + 64, w3 >> 16);
      sts16(a4 + 16 * r, w4); sts16(a4 + 16 * r + 32, w4 >> 16);
    }
  }
  if (lane == 0) { sts16(kc + 2 * 640, pack_bf(k2048, 0.f)); sts32(kc - 4, 0); }
  __syncwarp();
  const uint32_t td = tb + T_D + 32;
#pragma unroll
  for (int hf = 0; hf < 2; hf++) {
    const uint2 v = lds64(kc + 256 * hf + 8 * lane);
    const uint32_t pv = lds32(kc + 256 * hf + 8 * lane - 4);
    sts128(td + 512 * hf + 16 * lane, __byte_perm(v.x, pv, 0x7610), __byte_perm(v.x, v.x, 0x1032), __byte_perm(v.y, v.x, 0x7610),
           __byte_perm(v.y, v.y, 0x1032));
  }
#pragma unroll
  for (int hf = 0; hf < 2; hf++) {
    const uint32_t v = lds32(kc + 512 + 128 * hf + 4 * lane), nx = lds32(kc + 516 + 128 * hf + 4 * lane);
    uint32_t w0 = __byte_perm(v, v, 0x1010);
    const uint32_t w1 = w0;
    if (hf == 0) { const uint32_t pv = lds32(kc + 508); if (lane == 0) w0 = __byte_perm(v, pv, 0x7610); }
    sts128(td + 1024 + 512 * hf + 16 * lane, w0, w1, __byte_perm(v, v, 0x1032), __byte_perm(nx, v, 0x7610));
  }
  {
    const uint32_t kk = lds16(kc + 2 * 384);
    const uint32_t w = lane < 3 ? (kk | (kk << 16)) : (lane == 3 ? (kk << 16) : 0u);
    if (lane < 24) sts32(td + 4 * (lane < 16 ? 512 + lane : lane - 24), w);
    const uint32_t lo_ = lds16(kc + 2 * 511), le_ = lds16(kc + 2 * 512);
    const uint32_t ja = tb + T_5 + (lane < 16 ? 4 * lane : 256 + 4 * lane);
    sts32(ja, lane == 16 ? (le_ << 16) : 0u);
    sts32(ja + 384, lane == 16 ? (lo_ << 16) : 0u);
    sts32(tb + (lane < 16 ? T_7 : T_9 - 64) + 4 * lane, 0u);
  }
#pragma unroll
  for (int s = 0; s < 2; s++) {
    const uint32_t b = kc + 2 * (s ? 512 : 384) + 8 * lane;
    const uint2 v = lds64(b);
    uint32_t em = lds16(b - 2), e0 = v.x;
    const uint32_t e4 = lds16(b + 8);
    if (lane == 0) { em = 0; e0 = 0; }
    sts64(tb + (s ? T_7 : T_3) + 64 + 8 * lane, __byte_perm(v.x, em, 0x5432), __byte_perm(v.y, v.x, 0x7632));
    sts64(tb + (s ? T_9 : T_5) + 64 + 8 * lane, __byte_perm(v.y, e0, 0x5410), __byte_perm(e4, v.y, 0x5410));
  }
  __syncwarp();
}

__device__ __forceinline__ uint32_t box2w(int lo, int n, int o) {
  return ((unsigned)(o - lo) < (unsigned)n ? 0x3F80u : 0u) | ((unsigned)(o + 1 - lo) < (unsigned)n ? 0x3F800000u : 0u);
}

__device__ __forceinline__ void conv_channel(uint32_t ub, uint32_t tb, int lane, uint4* ydst) {
  const int g = lane >> 2, c = lane & 3, x = g - 2 * c;
  const int mi = lane >> 3;
  const uint32_t qa = ub + U_PAD + 16 * (lane & 7) + ((mi == 0 || mi == 3) ? U_ODD : 0) - (mi == 0 ? 16 : 0);
  const uint32_t hb = ub + U_PAD + (mi & 1) * U_ODD + 16 * ((lane >> 4) + (lane & 7)) - 16;
  const uint32_t kv = lds16(tb + T_KC + 16 + 2 * 512);
  const int oh = c < 2 ? 8 + 2 * c : 2 * c - 8, og = c < 3 ? 2 * c : -10;
  uint32_t bx[4] = {box2w(g - 4, 9, 2 * c), box2w(g - 3, 7, 2 * c), box2w(g - 4, 9, oh), box2w(g - 3, 7, oh)};
  uint32_t by[4] = {box2w(g - 10, 5, 2 * c - 8), box2w(g - 5, 3, 2 * c - 8), box2w(g - 10, 5, og), box2w(g - 5, 3, og)};
  uint32_t lb0 = ((unsigned)(x + 5) < 2u ? kv : 0u) | ((unsigned)(x + 4) < 2u ? kv << 16 : 0u);
  uint32_t lb1 = ((unsigned)(x - 3) < 2u ? kv : 0u) | ((unsigned)(x - 4) < 2u ? kv << 16 : 0u);
  const int q0 = g - 1, q1 = c < 3 ? g : g - 2;
  uint32_t y0a = ub + U_PAD + (q0 & 1) * U_ODD + 16 * (q0 >> 1) + 4 * c;
  uint32_t y1a = ub + U_PAD + (q1 & 1) * U_ODD + 16 * (q1 >> 1) + 4 * c;
#pragma unroll
  for (int i = 0; i < 4; i++) asm volatile("" : "+r"(bx[i]), "+r"(by[i]));
  asm volatile("" : "+r"(lb0), "+r"(lb1), "+r"(y0a), "+r"(y1a));
  mbar_wait(BAR(MB_UFULL));
  mbar_spin(BAR(MB_EMPTY + 15));
  TS(36);
  float acc[16][4];
  {
    uint32_t z09[8], z07[8], zm9[8], zm7[8];
#pragma unroll
    for (int i = 0; i < 8; i++) {
      uint32_t h[4];
      ldsm4(h, hb + 128 * i);
      float y0, y1, y2, y3, w0, w1, w2, w3;
      mma0(y0, y1, y2, y3, bx[0], bx[1], bx[2], bx[3], h[2], c < 2 ? h[3] : h[1]);
      mma0(w0, w1, w2, w3, bx[0], bx[1], bx[2], bx[3], h[1], c < 2 ? h[2] : h[0]);
      z09[i] = pack_bf(y0, y1); z07[i] = pack_bf(y2, y3);
      zm9[i] = pack_bf(w0, w1); zm7[i] = pack_bf(w2, w3);
    }
  uint32_t f3[3][4][4];
  {
    const uint32_t fa = tb + T_7 + 4 * (16 + x);
#pragma unroll
    for (int tt = 0; tt < 3; tt++)
#pragma unroll
      for (int D = 0; D < 4; D++) {
        const uint32_t a = fa + (tt == 0 ? 316 : (tt == 1 ? 320 : 0)) + 64 * D;
        f3[tt][D][0] = lds32(a); f3[tt][D][1] = lds32(a + 32); f3[tt][D][2] = lds32(a - 32); f3[tt][D][3] = lds32(a);
      }
  }
    float a[4][2][4];
#pragma unroll
    for (int kap = 0; kap < 4; kap++)
#pragma unroll
      for (int sg = 0; sg < 2; sg++)
#pragma unroll
        for (int bk = 3; bk >= kap; bk--) {
          const uint32_t(&q0_)[4] = f3[sg ? 2 : 0][bk - kap];
          const uint32_t(&q1_)[4] = f3[sg ? 2 : 1][bk - kap];
          float(&a0)[4] = a[bk][0];
          float(&a1)[4] = a[bk][1];
          if (sg == 0 && kap == 0) {
            mma0(a0[0], a0[1], a0[2], a0[3], q0_[0], q0_[1], q0_[2], q0_[3], z09[0], z09[1]);
            mma0(a1[0], a1[1], a1[2], a1[3], q1_[0], q1_[1], q1_[2], q1_[3], zm9[0], zm9[1]);
          } else {
            mma(a0[0], a0[1], a0[2], a0[3], q0_[0], q0_[1], q0_[2], q0_[3], sg ? zm7[2 * kap] : z09[2 * kap], sg ? zm7[2 * kap + 1] : z09[2 * kap + 1]);
            mma(a1[0], a1[1], a1[2], a1[3], q1_[0], q1_[1], q1_[2], q1_[3], sg ? z07[2 * kap] : zm9[2 * kap], sg ? z07[2 * kap + 1] : zm9[2 * kap + 1]);
          }
        }
    SPLIT();
#pragma unroll
    for (int i = 0; i < 8; i++) {
      uint32_t h[4];
      ldsm4(h, qa + 128 * i);
      const float ci[4] = {a[i >> 1][0][2 * (i & 1)], a[i >> 1][0][2 * (i & 1) + 1], a[i >> 1][1][2 * (i & 1)], a[i >> 1][1][2 * (i & 1) + 1]};
      mmac(acc[8 + i], h[0], h[1], h[2], h[3], lb0, lb1, ci);
    }
  }
  TS(44);
  {
    uint2 a5[10], a3[10];
    const uint32_t aa = tb + T_5 + 4 * (8 + 2 * g - 2 * c);
#pragma unroll
    for (int m = 0; m < 10; m++) { a5[m] = lds64(aa + 32 * m); a3[m] = lds64(aa + 384 + 32 * m); }
    uint32_t x5[12][2], x3[12][2];
    auto ygen = [&](int kap) {
#pragma unroll
      for (int hh = 0; hh < 2; hh++) {
        float y0, y1, y2, y3;
        mma0(y0, y1, y2, y3, by[0], by[1], by[2], by[3], lds32(y0a + 128 * kap + 64 * hh), lds32(y1a + 128 * kap + 64 * hh));
        x5[kap][hh] = pack_bf(y0, y1);
        x3[kap][hh] = pack_bf(y2, y3);
      }
    };
    ygen(11); ygen(10); ygen(9); ygen(8);
#pragma unroll
    for (int kap = 11; kap >= 0; kap--) {
      if (kap >= 4) ygen(kap - 4);
#pragma unroll
      for (int sg = 0; sg < 2; sg++)
#pragma unroll
        for (int i = 4; i >= 0; i--) {
          const int be = kap + 4 + i;
          if (be <= 15) {
            const uint2 &hi = sg ? a3[2 * i + 1] : a5[2 * i + 1], &lo = sg ? a3[2 * i] : a5[2 * i];
            const uint32_t b0 = sg ? x3[kap][0] : x5[kap][0], b1 = sg ? x3[kap][1] : x5[kap][1];
            if (be < 8 && i == 0 && sg == 0) mma0(acc[be][0], acc[be][1], acc[be][2], acc[be][3], hi.x, hi.y, lo.x, lo.y, b0, b1);
            else mma(acc[be][0], acc[be][1], acc[be][2], acc[be][3], hi.x, hi.y, lo.x, lo.y, b0, b1);
          }
        }
    }
  }
  TS(45);
  {
    const uint32_t st = tb + T_ST + lane * 8;
#pragma unroll
    for (int be = 4; be < 12; be++) sts64(st + 256 * be, pack_bf(acc[be][0], acc[be][1]), pack_bf(acc[be][2], acc[be][3]));
    SPLIT();
    uint32_t F[66], qd[8][4];
    const uint32_t fa = tb + T_D + 32 + 4 * x;
#pragma unroll
    for (int i = 0; i < 32; i++) {
      const int s = 120 - (i >> 2) - 8 * (i & 3);
      uint32_t(&q)[4] = qd[i & 7];
      ldsm4(q, qa + 16 * s);
      const int m = 16 * (i & 3) + 2 * (i >> 2);
      F[m] = lds32(fa + 32 * m); F[m + 1] = lds32(fa + 32 * m + 32);
#pragma unroll
      for (int be = 15; be >= 12; be--) {
        const int de = 8 * be - s;
        float(&a)[4] = (be >= 14 && !(i & 1)) ? acc[be - 4] : acc[be];
        if (de >= 0 && be >= 14 && i == 2 * (15 - be)) mma0(a[0], a[1], a[2], a[3], q[0], q[1], q[2], q[3], F[2 * de + 1], F[2 * de]);
        else if (de >= 0) mma(a[0], a[1], a[2], a[3], q[0], q[1], q[2], q[3], F[2 * de + 1], F[2 * de]);
      }
    }
#pragma unroll
    for (int i = 0; i < 8; i++) acc[14 + (i >> 2)][i & 3] += acc[10 + (i >> 2)][i & 3];
    F[64] = lds32(fa + 32 * 64); F[65] = lds32(fa + 32 * 65);
    uint32_t qp = qa + 128 * 11, sta = st + 256 * 10;
    uint4* yd = ydst + 7 * 32;
#pragma unroll
    for (int i = 0; i < 6; i++) ldsm4(qd[i], qp - 16 * i);
    uint2 sv = lds64(sta + 256);
    float ci[4] = {bf_lo(sv.x), bf_hi(sv.x), bf_lo(sv.y), bf_hi(sv.y)};
    float T[5][4];
#pragma unroll
    for (int i = 0; i < 16; i++) T[i >> 2][i & 3] = acc[12 + (i >> 2)][i & 3];
    nb_sync(NB_YZ, 160);
    TS(46);
#pragma unroll 1
    for (int bp = 5; bp >= 0; bp--) {
      uint32_t held[2];
#pragma unroll
      for (int o = 1; o >= 0; o--) {
#pragma unroll
        for (int k = 4; k >= 1; k--) mmac(T[k], qd[0][0], qd[0][1], qd[0][2], qd[0][3], F[16 * k + 1], F[16 * k], T[k - 1]);
        mmac(T[0], qd[0][0], qd[0][1], qd[0][2], qd[0][3], F[1], F[0], ci);
        ldsm4(qd[6], qp - 16 * 6);
        ldsm4(qd[7], qp - 16 * 7);
        sv = lds64(sta);
#pragma unroll
        for (int i = 1; i < 8; i++) {
#pragma unroll
          for (int k = 3; k >= 0; k--)
            mma(T[k][0], T[k][1], T[k][2], T[k][3], qd[i][0], qd[i][1], qd[i][2], qd[i][3], F[16 * k + 2 * i + 1], F[16 * k + 2 * i]);
          if (i < 7) ldsm4(qd[i - 1], qp - 128 - 16 * (i - 1));
          if (i == 2) {
            const uint32_t w0 = pack_bf(T[4][0], T[4][1]), w1 = pack_bf(T[4][2], T[4][3]);
            if (o) { held[0] = w0; held[1] = w1; }
            else st_x(yd, nz(w0), w1, held[0], held[1]);
          }
          if (i == 4) {
            if (2 * bp + o <= 4) sv = make_uint2(0, 0);
            ci[0] = bf_lo(sv.x); ci[1] = bf_hi(sv.x); ci[2] = bf_lo(sv.y); ci[3] = bf_hi(sv.y);
          }
        }
        qp -= 128; sta -= 256;
      }
      yd -= 32;
      if (!(bp & 1)) nb_arrive(NB_Y + 1 + (bp >> 1), 160);
    }
#pragma unroll
    for (int B = 1; B >= 0; B--)
      st_x(ydst + B * 32, nz(pack_bf(T[2 * B][0], T[2 * B][1])), pack_bf(T[2 * B][2], T[2 * B][3]),
           pack_bf(T[2 * B + 1][0], T[2 * B + 1][1]), pack_bf(T[2 * B + 1][2], T[2 * B + 1][3]));
  }
}

__device__ __forceinline__ void dual_exp(const uint32_t* w, uint32_t* e) {
  const float L = 1.44268798828125f;
  uint32_t mx = bmax2(bmax2(w[0], w[1]), bmax2(w[2], w[3]));
  uint32_t mn = bmin2(bmin2(w[0], w[1]), bmin2(w[2], w[3]));
  mx = bmax2(mx, __shfl_xor_sync(0xffffffffu, mx, 1));
  mn = bmin2(mn, __shfl_xor_sync(0xffffffffu, mn, 1));
  mx = bmax2(mx, __shfl_xor_sync(0xffffffffu, mx, 2));
  mn = bmin2(mn, __shfl_xor_sync(0xffffffffu, mn, 2));
  const float mx0 = bf_lo(mx) * -L, mx1 = bf_hi(mx) * -L, mn0 = bf_lo(mn) * L, mn1 = bf_hi(mn) * L;
#pragma unroll
  for (int i = 0; i < 2; i++) {
    const float a0 = bf_lo(w[2 * i]), a1 = bf_hi(w[2 * i]), b0 = bf_lo(w[2 * i + 1]), b1 = bf_hi(w[2 * i + 1]);
    e[2 * i] = pack_bf(ex2(fmaf(a0, L, mx0)), ex2(fmaf(b0, L, mx0)));
    e[2 * i + 1] = pack_bf(ex2(fmaf(a1, L, mx1)), ex2(fmaf(b1, L, mx1)));
    e[4 + 2 * i] = pack_bf(ex2(fmaf(a0, -L, mn0)), ex2(fmaf(b0, -L, mn0)));
    e[5 + 2 * i] = pack_bf(ex2(fmaf(a1, -L, mn1)), ex2(fmaf(b1, -L, mn1)));
  }
}
__device__ __forceinline__ void normalise(uint32_t* e, const float (&s)[4]) {
  const uint32_t r = pack_bf(rcp(s[0]), rcp(s[2]));
  const __nv_bfloat162 rr = *(const __nv_bfloat162*)&r;
#pragma unroll
  for (int i = 0; i < 4; i++) {
    const __nv_bfloat162 v = __hmul2(*(const __nv_bfloat162*)&e[i], (i & 1) ? __high2bfloat162(rr) : __low2bfloat162(rr));
    e[i] = *(const uint32_t*)&v;
  }
}
__host__ __device__ constexpr uint64_t qdesc(uint32_t addr) { return mkdesc(addr, 128, 256, 0); }

__global__ void __launch_bounds__(NTHREADS, 1)
fused_kernel(const Params P, const __grid_constant__ CUtensorMap mx, const __grid_constant__ CUtensorMap mw,
             const __grid_constant__ CUtensorMap mo, const __grid_constant__ CUtensorMap mu,
             const __grid_constant__ CUtensorMap mout, const __grid_constant__ CUtensorMap mw4) {
  constexpr uint32_t sb = SB;
  const int tid = threadIdx.x, lane = tid & 31;
  const int warp = __shfl_sync(0xffffffffu, tid >> 5, 0);
  const int b = blockIdx.x, oct = b >> 3, i8 = b & 7;
  const int rt = (((oct & 4) ? ~oct : oct) & 3) * 2 + (i8 >> 2);
  const int hp = (oct >> 2) * 4 + (i8 & 3);

  const int wg = warp >> 2, w = warp & 3;
  const int d = b * 4 + ((tid >> 5) & 3);
  const KgenRaw raw = kgen_load(P, d, tid >> 7, lane);
  const unsigned short dsk = __ldg((const unsigned short*)P.Dskip + d);
  if (tid < 384) {
    asm volatile("prefetch.tensormap [%0];" ::"l"(&mu) : "memory");
    asm volatile("prefetch.tensormap [%0];" ::"l"(&mw) : "memory");
    asm volatile("prefetch.tensormap [%0];" ::"l"(&mx) : "memory");
    asm volatile("prefetch.tensormap [%0];" ::"l"(&mw4) : "memory");
  }
  if (warp == 12) {
    if (lane == 0) {
#pragma unroll
      for (int i = 0; i < 9; i++) mbar_init(BAR(i), 1);
      asm volatile("fence.mbarrier_init.release.cluster;" ::: "memory");
    }
    __syncwarp();
    if (lane < 9) mbar_expect(BAR(0) + 8 * lane, (lane == 5 || lane == 7) ? 40960 : ((lane == 0 || lane > 5) ? 16384 : 28672));
    __syncwarp();
    e_tma3d(sb + OFF_W, &mw, BAR(MB_FULL), hp * 32, 0, 0);
    e_tma2d(sb + OFF_X + 3 * 16384, &mx, BAR(MB_FULL), 0, rt * 256);
    nb_arrive(NB_PROD, 192);
  } else if (warp == 14) {
    e_prefetch(P.x + (size_t)(rt * 256 + hp * 8) * 512, 8192);
  } else if (warp == 13) {
    if (lane == 0) {
#pragma unroll
      for (int i = 9; i < 39; i++) mbar_init(BAR(i), i < MB_EMPTY ? 1 : (i < MB_AUX ? 4 : 8));
      asm volatile("fence.mbarrier_init.release.cluster;" ::: "memory");
    }
    __syncwarp();
    if (lane < 13 && lane != 9) mbar_expect(BAR(MB_FULL + 8) + 8 * lane, lane < 8 ? 16384 : (lane == 8 ? 131072 : (lane == 10 ? 8192 : (lane == 11 ? 24576 : 32768))));
    nb_arrive(NB_PROD, 192);
  }
  const uint32_t tb = sb + OFF_T + w * T_CH;
  const uint32_t kp = wg >= 2 ? sb + OFF_STG0 + 16384 + w * 2048 : ((tb + 127) & ~127u) + wg * 2048;
  const KgenAddr kad = kgen_addr(lane, wg == 3 ? sb + OFF_X + 32768 + w * 2048 : kp);
  if (wg == 1) nb_sync(NB_PROD, 192);
  if (warp == 12) {
#pragma unroll 1
    for (int kb = 1; kb < 4; kb++) {
      if (kb == U_AT) e_tma4d(sb + OFF_STG0, &mu, BAR(MB_URAW), i8 * 64, oct * 2);
      e_tma3d(sb + OFF_W + kb * 12288, &mw, BAR(MB_FULL) + 8 * kb, hp * 32, kb * 64, 0);
      e_tma2d(sb + OFF_X + (kb < 2 ? kb + 3 : kb - 2) * 16384, &mx, BAR(MB_FULL) + 8 * kb, kb * 64, rt * 256);
    }
    e_tma4d(sb + OFF_W + 4 * 12288, &mw4, BAR(MB_FULL + 4), hp * 32, 4);
    e_tma4d(sb + OFF_W + 6 * 12288, &mw4, BAR(MB_FULL + 6), hp * 32, 6);
    if (smem_u32(smem_raw) != SB) __trap();
    if (lane == 0) TS1(54);
  }
  float k[5][4], k2048, ksc;
  kgen_unit(raw, kad, blockIdx.y, k, k2048, ksc);
  TS(40 + wg);
  if ((fu(k[0][0]) & fu(k[1][0]) & fu(k[2][0]) & fu(k[3][0]) & fu(k[4][0])) == 0xffffffffu) sts32(kp, 0);
  if (wg == 3) {
    nb_sync(0, 512);
    if (warp == 12) {
      asm volatile("fence.proxy.async.shared::cta;" ::: "memory");
      e_tma2d(sb + OFF_X + 2 * 16384, &mx, BAR(MB_FULL + 4), 256, rt * 256);
      if (X2_AT < 0) e_prefetch(P.x + (size_t)(rt * 256 + 128 + hp * 8) * 512, 8192);
    }
  } else if (wg) {
    nb_arrive(0, 512);
  }
  k2048 += __shfl_xor_sync(0xffffffffu, k2048, 16);
  k2048 += __shfl_xor_sync(0xffffffffu, k2048, 8);
  if (wg != 2) {
    uint32_t h[10];
#pragma unroll
    for (int j = 0; j < 10; j++) h[j] = hu(__floats2half2_rn(k[j >> 1][2 * (j & 1)], k[j >> 1][2 * (j & 1) + 1]));
    sts128(kp + lane * 16, h[0], h[1], h[2], h[3]);
    sts128(kp + 512 + lane * 16, h[4], h[5], h[6], h[7]);
    sts128(kp + 1024 + lane * 16, h[8], h[9], fu(k2048), fu(ksc));
  }
  if (wg == 0) { nb_arrive(NB_PREP, 512); nb_sync(0, 512); }
  else if (wg != 2) nb_arrive(NB_PREP, 512);
  else nb_sync(NB_PREP, 512);
  if (warp >= 12) {
    asm volatile("setmaxnreg.dec.sync.aligned.u32 32;");
    if (warp == 12) {
      uint32_t slot = sb + OFF_X + 3 * 16384;
#pragma unroll 1
      for (int n = 0; n < 11; n++) {
        mbar_spin(BAR(MB_EMPTY) + 8 * n);
        const int m = n + 5;
        e_tma2d(slot, &mx, BAR(MB_FULL) + 8 * m, (m & 7) * 64, rt * 256 + (m >> 3) * 128);
        slot = slot == sb + OFF_X + 4 * 16384 ? sb + OFF_X : slot + 16384;
        if (n == X2_AT) e_prefetch(P.x + (size_t)(rt * 256 + 128 + hp * 8) * 512, 8192);
        if (n == 7) {
          e_prefetch(P.wo + (size_t)b * 2048, 4096);
          asm volatile("prefetch.tensormap [%0];" ::"l"(&mo) : "memory");
          asm volatile("prefetch.tensormap [%0];" ::"l"(&mout) : "memory");
        }
      }
#pragma unroll 1
      for (int i = 0; i < 8; i++) {
        mbar_wait(BAR(MB_EMPTY + 10) + 8 * ((0x54332222u >> (4 * i)) & 7));
        const int w0 = (0x54736210u >> (4 * i)) & 7;
        e_tma3d(sb + OFF_W + w0 * 16384, &mo, BAR(MB_WO), 0, w0 * 64, (hp & 3) * 2);
      }
    } else {
      if (warp == 15) {
        const uint4 v0 = __ldg((const uint4*)P.wphi + hp * 64 + lane), v1 = __ldg((const uint4*)P.wphi + hp * 64 + 32 + lane);
        sts128(sb + OFF_PHI + (lane & 1) * 256 + (lane >> 1) * 16, v0.x, v0.y, v0.z, v0.w);
        sts128(sb + OFF_PHI + 512 + (lane & 1) * 256 + (lane >> 1) * 16, v1.x, v1.y, v1.z, v1.w);
        const uint32_t one = (((lane >> 3) ^ (lane >> 4)) & 1) ? 0u : ((lane & 1) ? 0x3F800000u : 0x3F80u);
        const int q = (lane >> 1) & 3;
        sts128(sb + OFF_EYE + lane * 16, q == 0 ? one : 0u, q == 1 ? one : 0u, q == 2 ? one : 0u, q == 3 ? one : 0u);
        sts64(sb + OFF_ONE + lane * 8, 0x3F803F80u, 0x3F803F80u);
        asm volatile("fence.proxy.async.shared::cta;" ::: "memory");
        nb_arrive(NB_KREAD, 160);
      }
      uint32_t* cnt = (uint32_t*)(P.xs + X_CNT) + (warp == 13 ? i8 : (warp == 14 ? 8 + rt : 16 + oct)) * 32;
      const unsigned target = (ld_x32(cnt) & ~15u) + 16;
      if (warp != 14) {
        if (warp == 15) mbar_wait(BAR(MB_EMPTY + ZERO_STEP));
        uint4* pz = P.xs + (warp == 13 ? X_PART + (hp * 8 + rt) * 144 : X_Y + b * 1024) + lane;
#pragma unroll 1
        for (int i = (warp == 13 ? 144 : 1024) - lane; i > 0; i -= 32, pz += 32) st_x(pz, 0, 0, 0, 0);
      }
      if (warp == 15) __syncwarp();
      else nb_sync(warp == 13 ? NB_INIT : NB_ODONE, warp == 13 ? 160 : 288);
      if (lane == 0) asm volatile("red.release.gpu.global.add.u32 [%0], %1;" ::"l"(cnt), "r"(warp == 15 ? 2 : 1) : "memory");
      if (lane == 0) TS1(warp == 13 ? 50 : (warp == 14 ? 57 : 53));
      asm volatile("fence.proxy.async.shared::cta;" ::: "memory");
      if (warp == 13) cnt += ((lane & 1 ? b >> 4 : i8 ^ (lane & 4)) - i8) * 32;
#pragma unroll 1
      for (int i = 0; i < SPIN_MAX; i++) {
        unsigned v;
        asm volatile("ld.acquire.gpu.global.u32 %0, [%1];" : "=r"(v) : "l"(cnt) : "memory");
        if (__all_sync(0xffffffffu, (int)(v - target) >= 0)) break;
      }
      if (lane == 0) TS1(warp == 13 ? 51 : (warp == 14 ? 58 : 55));
      if (warp == 15) { nb_arrive(NB_YZ, 160); return; }
      asm volatile("fence.proxy.async.global;" ::: "memory");
      if (warp == 13) {
        mbar_wait(BAR(MB_EMPTY + 11));
        e_expect(BAR(MB_UFULL), 4 * U_CH);
        e_bulk(sb + OFF_U, P.xs + X_UT + b * (U_CH / 4), 4 * U_CH, BAR(MB_UFULL));
      } else {
        const uint4* src = P.xs + X_O + (rt * 4 + (hp >> 2)) * 4096;
        e_bulk(sb + OFF_X + 32768 + 57344, src + 3584, 8192, BAR(MB_OA));
        e_bulk(sb + OFF_X + 32768, src, 32768, BAR(MB_OC));
        e_bulk(sb + OFF_STG0, src + 3200, 6144, BAR(MB_OB));
        nb_sync(NB_BDONE, 288);
        asm volatile("fence.proxy.async.shared::cta;" ::: "memory");
        e_bulk(sb + OFF_U, src + 2048, 18432, BAR(MB_OB));
      }
    }
    return;
  }

  const int t = tid & 127;
  const int g = lane >> 2, c = lane & 3;
  if (wg == 1) {
    mbar_wait(BAR(MB_URAW));
    TS(48);
    uint4* dst = P.xs + X_UT + (i8 * 64 + g) * (U_CH / 16) + (w & 1) * (U_ODD / 16) + U_PAD / 16 + oct * 8 + (w >> 1) * 4 + c;
    const int ln = ((lane >> 1) & 3) + 4 * (lane & 1);
    uint32_t r[8][4];
#pragma unroll
    for (int i = 0; i < 8; i++) ldsm4t(r[i], sb + OFF_STG0 + w * 4096 + ((lane >> 3) * 8 + ln) * 128 + ((i ^ ln) << 4));
#pragma unroll
    for (int i = 0; i < 8; i++) dst[i * (U_CH / 2)] = make_uint4(r[i][0], r[i][1], r[i][2], r[i][3]);
    nb_arrive(NB_INIT, 160);
    if (lane == 0) mbar_arrive(BAR(MB_AUX));
  }
  {
    if (wg == 2) {
      asm volatile("setmaxnreg.inc.sync.aligned.u32 160;");
#pragma unroll
      for (int j = 0; j < 5; j++) { k[j][0] *= ksc; k[j][1] *= ksc; k[j][2] *= ksc; k[j][3] *= ksc; }
#pragma unroll 1
      for (int q = 0; q < 3; q++) {
        const uint32_t src = (q == 2 ? kp : ((tb + 127) & ~127u) + q * 2048) + lane * 16;
        const uint4 v0 = lds128(src), v1 = lds128(src + 512), v2 = lds128(src + 1024);
        const uint32_t h[10] = {v0.x, v0.y, v0.z, v0.w, v1.x, v1.y, v1.z, v1.w, v2.x, v2.y};
#pragma unroll
        for (int j = 0; j < 10; j++) {
          const float2 f = __half22float2(*(const __half2*)&h[j]);
          k[j >> 1][2 * (j & 1)] = fmaf(f.x, uf(v2.w), k[j >> 1][2 * (j & 1)]);
          k[j >> 1][2 * (j & 1) + 1] = fmaf(f.y, uf(v2.w), k[j >> 1][2 * (j & 1) + 1]);
        }
        k2048 += uf(v2.z);
      }
#pragma unroll
      for (int o2 = 4; o2; o2 >>= 1) k2048 += __shfl_xor_sync(0xffffffffu, k2048, o2);
      if (lane == 0) k[0][0] += bf_lo(dsk);
      __syncwarp();
      if (lane == 0) mbar_arrive(BAR(MB_AUX));
      TS(34);
      build_tables(tb, lane, k, k2048);
      TS(35);
      uint4* const g_y = P.xs + X_Y;
      conv_channel(sb + OFF_U + w * U_CH, tb, lane, g_y + (size_t)d * 256 + lane);
      nb_arrive(NB_BDONE, 288);
      nb_arrive(NB_Y, 160);
      TS(37);
      if (w == 0) TSDUMP(32);
      return;
    }
    if (wg == 1) {
      mbar_wait(BAR(MB_EMPTY + 4));
      mbar_spin(BAR(MB_EMPTY + 6));
    }
    TS(wg * 16 + 1);
  }

  float acc[2][48];
  {
    uint32_t fb = BAR(MB_FULL) + 64 * wg;
    uint32_t da = (uint32_t)mkdesc(sb + OFF_X, 16, 0, 0) + (wg ? 1024 : 3072), db = (uint32_t)mkdesc(sb + OFF_W, 4096, 0, 0);
    constexpr uint64_t ha = mkdesc(0, 0, 1024, 1), hb = mkdesc(0, 0, 512, 2);
    mbar_spin(fb);
    TS(wg * 16 + 2);
#pragma unroll 1
    for (int kb = 0; kb < 8; kb++) {
      WG_FENCE();
#pragma unroll
      for (int k = 0; k < 4; k++) {
        wgmma_ss_n96(acc[0], ha | (da + 2 * k), hb | (db + 64 * k), k ? 1 : kb);
        wgmma_ss_n96(acc[1], ha | (da + 2 * k + 512), hb | (db + 64 * k), k ? 1 : kb);
      }
      WG_COMMIT();
      if (kb < 7) mbar_spin(fb + 8);
      WG_WAIT(1);
      if (kb > 0) e_arrive(fb + 8 * (MB_EMPTY - MB_FULL - 1));
      fb += 8; db += 768;
      da = da == (uint32_t)mkdesc(sb + OFF_X + 65536, 16, 0, 0) ? da - 4096 : da + 1024;
    }
    if (wg == 0) nb_sync(NB_KREAD, 160);
    asm volatile("setmaxnreg.inc.sync.aligned.u32 160;");
    WG_WAIT(0);
    e_arrive(fb + 8 * (MB_EMPTY - MB_FULL - 1));
    SPLIT();
  }
  TS(wg * 16 + 3);

  constexpr uint32_t stg0 = sb + OFF_STG0, stg1 = sb + OFF_X + 32768;
  uint4* const g_part = P.xs + X_PART;
  uint4* const g_o = P.xs + X_O;
  constexpr uint32_t kvs = stg0;
  auto pack8 = [](const float* a) { return make_uint4(pack_bf(a[0], a[1]), pack_bf(a[2], a[3]), pack_bf(a[4], a[5]), pack_bf(a[6], a[7])); };
  auto feat = [&](const uint4 (&af)[4], float (&p)[4][8]) {
    WG_FENCE();
#pragma unroll
    for (int u = 0; u < 4; u++) wgmma_rs_n16(p[u], af[u], qdesc(sb + OFF_PHI + (u & 1) * 512), 0);
    WG_COMMIT();
  };
  auto packp = [](const float (&p)[4][8], uint32_t (&pw)[16]) {
#pragma unroll
    for (int i = 0; i < 16; i++) pw[i] = pack_bf(p[i >> 2][(i & 1) + 2 * (i & 2)], p[i >> 2][(i & 1) + 2 * (i & 2) + 2]);
  };
  auto contract = [&](float (&kc)[20], uint32_t stg, int acc_in) {
    WG_FENCE();
#pragma unroll
    for (int s = 0; s < 8; s++) wgmma_ss_n40(kc, qdesc(stg + s * SLAB), qdesc(stg + s * SLAB + 2048), s ? 1 : acc_in);
    WG_COMMIT();
    WG_WAIT(0);
  };
  uint32_t eq[32];
  {
    uint4 af[4], aq[4], vp[4];
    float p[4][8];
#pragma unroll
    for (int u = 0; u < 4; u++) af[u] = pack8(acc[u >> 1] + 16 + 8 * (u & 1));
    feat(af, p);
#pragma unroll
    for (int u = 0; u < 4; u++) { aq[u] = pack8(acc[u >> 1] + 8 * (u & 1)); vp[u] = pack8(acc[u >> 1] + 32 + 8 * (u & 1)); }
    WG_WAIT(0);
    uint32_t pw[16], ek[32];
    packp(p, pw);
#pragma unroll
    for (int u = 0; u < 4; u++) dual_exp(pw + 4 * u, ek + 8 * u);
    TS(wg * 16 + 12);
    mbar_spin(wg ? BAR(MB_EMPTY + 15) : BAR(MB_AUX));
    float rs[8][4];
    WG_FENCE();
#pragma unroll
    for (int i = 0; i < 8; i++) wgmma_rs_n8(rs[i], make_uint4(ek[4 * i], ek[4 * i + 1], ek[4 * i + 2], ek[4 * i + 3]), qdesc(sb + OFF_ONE), 0);
    WG_COMMIT();
    feat(aq, p);
    const uint32_t sl = (wg ? stg1 : stg0) + w * SLAB + lane * 16;
#pragma unroll
    for (int i = 0; i < 4; i++) stsm4(sl + (i >> 1) * 4 * SLAB + 2048 + (i & 1) * 512, vp[i].x, vp[i].y, vp[i].z, vp[i].w);
    sts128(sl + (lane >> 4) * (4 * SLAB - 256) + 3072, 0x3F803F80u, 0x3F803F80u, 0x3F803F80u, 0x3F803F80u);
    WG_WAIT(1);
#pragma unroll
    for (int i = 0; i < 8; i++) {
      normalise(ek + 4 * i, rs[i]);
      stsm4(sl + (i >> 2) * 4 * SLAB + (i & 3) * 512, ek[4 * i], ek[4 * i + 1], ek[4 * i + 2], ek[4 * i + 3]);
    }
    asm volatile("fence.proxy.async.shared::cta;" ::: "memory");
    TS(wg * 16 + 13);
    if (wg) {
      nb_arrive(NB_ST0, 256);
    } else {
      float kc[20];
      uint4* pp = g_part + (size_t)(hp * 8 + rt) * 144 + t;
      uint32_t* pz = (uint32_t*)(pp - t + 128) + w * 16 + c * 8 + g;
      asm volatile("" : "+l"(pp), "+l"(pz));
      nb_sync(NB_WG0, 128);
      contract(kc, stg0, 0);
      mbar_wait(BAR(MB_UFULL));
      TS(15);
      nb_sync(NB_ST0, 256);
      contract(kc, stg1, 1);
      TS(6);
      float kv[8];
#pragma unroll
      for (int i = 0; i < 8; i++) kv[i] = w & 2 ? kc[8 + i] : kc[i];
      st_x(pp, nz(pack_bf(kv[0], kv[1])), pack_bf(kv[2], kv[3]), pack_bf(kv[4], kv[5]), pack_bf(kv[6], kv[7]));
      if (c < 2) st_x32(pz, nz(fu(c ? kc[18] : kc[16])));
      TS(5);
    }
    SPLIT();
    WG_WAIT(0);
    packp(p, pw);
#pragma unroll
    for (int u = 0; u < 4; u++) dual_exp(pw + 4 * u, eq + 8 * u);
    SPLIT();
  }
  TS(wg * 16 + 4);
  if (wg == 1) {
    mbar_wait(BAR(MB_UFULL));
    const uint4* ps = g_part + (size_t)hp * 8 * 144 + t;
    const uint32_t* zs = (const uint32_t*)(g_part + (size_t)(hp * 8 + (lane >> 4) * 4) * 144 + 128) + w * 16 + (lane & 15);
    uint4 v[8];
    uint32_t zv[4];
#pragma unroll 1
    for (int it = 0; it < SPIN_MAX; it++) {
#pragma unroll
      for (int i = 0; i < 8; i++) v[i] = ld_x(ps + i * 144);
#pragma unroll
      for (int i = 0; i < 4; i++) zv[i] = ld_x32(zs + i * 576);
      uint32_t m = min(min(zv[0], zv[1]), min(zv[2], zv[3]));
#pragma unroll
      for (int i = 0; i < 8; i++) m = min(m, v[i].x);
      if (__all_sync(0xffffffffu, m != 0)) break;
    }
    float s[8];
    WG_FENCE();
#pragma unroll
    for (int r = 0; r < 8; r++) wgmma_rs_n16(s, v[r], qdesc(sb + OFF_EYE), r);
    WG_COMMIT();
    float zsum = (uf(zv[0]) + uf(zv[1])) + (uf(zv[2]) + uf(zv[3]));
    zsum += __shfl_xor_sync(0xffffffffu, zsum, 16);
    const uint32_t z1 = pack_bf(zsum, 1.f);
    if (lane < 16) sts128(kvs + w * 768 + 512 + lane * 16, z1, z1, z1, z1);
    WG_WAIT(0);
    stsm4(kvs + w * 768 + lane * 16, pack_bf(s[0], s[1]), pack_bf(s[2], s[3]), pack_bf(s[4], s[5]), pack_bf(s[6], s[7]));
    asm volatile("fence.proxy.async.shared::cta;" ::: "memory");
    TS(22);
  }
  nb_sync(NB_KV, 256);
  {
    float n[8][12];
    WG_FENCE();
#pragma unroll
    for (int i = 0; i < 8; i++) wgmma_rs_n24(n[i], make_uint4(eq[4 * i], eq[4 * i + 1], eq[4 * i + 2], eq[4 * i + 3]), qdesc(kvs + (i & 3) * 768), 0);
    WG_COMMIT();
    uint32_t* od = (uint32_t*)(g_o + (size_t)((rt * 4 + wg * 2) * 32 + hp * 2) * 128) + w * 64 + lane;
    WG_WAIT(0);
#pragma unroll
    for (int u = 0; u < 4; u++) {
      float(&np)[12] = n[2 * u];
      const float(&nm)[12] = n[2 * u + 1];
      const float q0 = np[9] * rcp(nm[9]), q1 = np[11] * rcp(nm[11]);
      const float r0 = rcp(fmaf(nm[8], q0, fmaf(np[9], 1e-6f, np[8]))), r1 = rcp(fmaf(nm[10], q1, fmaf(np[11], 1e-6f, np[10])));
#pragma unroll
      for (int i = 0; i < 8; i++) np[i] = fmaf(nm[i], (i & 2) ? q1 : q0, np[i]);
      uint32_t* o = od + (u >> 1) * 16384 + (u & 1) * 512;
      o[0] = pack_bf(np[0] * r0, np[1] * r0);
      o[32] = pack_bf(np[2] * r1, np[3] * r1);
      o[256] = pack_bf(np[4] * r0, np[5] * r0);
      o[288] = pack_bf(np[6] * r1, np[7] * r1);
      if (u == 1) SPLIT();
    }
  }
  TS(wg * 16 + 7);
  nb_arrive(NB_ODONE, 288);
  if (wg) {
    const uint4* src = P.xs + X_Y + (oct * 32 + c * 8) * 256 + (2 * w + (g >> 2)) * 32 + i8 * 4 + (g & 3);
    __nv_bfloat16* dst = P.out + (size_t)((2 * w + (g >> 2)) * 256 + i8 * 16 + (g & 3) * 2) * 1024 + 512 + oct * 32 + c * 8;
    nb_sync(NB_Y + w, 160);
    uint4 v[8];
#pragma unroll 1
    for (int it = 0; it < SPIN_MAX; it++) {
      uint32_t m = 0xffffffffu;
#pragma unroll
      for (int i = 0; i < 8; i++) v[i] = ld_x(src + i * 256);
#pragma unroll
      for (int i = 0; i < 8; i++) m = min(m, v[i].x);
      if (__all_sync(0xffffffffu, m != 0)) break;
    }
#pragma unroll
    for (int i = 0; i < 8; i++) *(uint4*)(dst + (size_t)((i >> 2) * 128 + ((i >> 1) & 1) * 8 + (i & 1)) * 1024) = tr_row(v, i);
    TS(31);
    GT(63);
    if (w == 0) TSDUMP(16);
    return;
  }
  mbar_wait(BAR(MB_WO));
  nb_sync(NB_BDONE, 288);
  TS(8);
  mbar_spin(BAR(MB_OA));
  TS(9);
  float oc[64];
  {
    constexpr uint64_t ha = mkdesc(0, 0, 128, 0), hb = mkdesc(0, 0, 1024, 1);
    constexpr uint32_t da0 = (uint32_t)mkdesc(stg1, 1024, 0, 0), db0 = (uint32_t)mkdesc(sb + OFF_W, 8192, 0, 0);
#pragma unroll 1
    for (int j = 0; j < 8; j++) {
      const int kb = (j + 7) & 7;
      if ((j & 3) == 1) mbar_spin(j == 1 ? BAR(MB_OC) : BAR(MB_OB));
      WG_FENCE();
#pragma unroll
      for (int k = 0; k < 4; k++) wgmma_ss_n128(oc, ha | (da0 + 512 * kb + 128 * k), hb | (db0 + 1024 * kb + 128 * k), k ? 1 : j);
      WG_COMMIT();
    }
    WG_WAIT(0);
  }
  TS(10);
  const uint32_t ot = ((sb + OFF_T + 1023) & ~1023u) + w * 4096;
#pragma unroll
  for (int hf = 0; hf < 2; hf++) {
#pragma unroll
    for (int i = 8 * hf; i < 8 * hf + 8; i += 2)
      stsm4(ot + hf * 2048 + (lane & 15) * 128 + (((i + (lane >> 4)) ^ lane) & 7) * 16, pack_bf(oc[4 * i], oc[4 * i + 1]),
            pack_bf(oc[4 * i + 2], oc[4 * i + 3]), pack_bf(oc[4 * i + 4], oc[4 * i + 5]), pack_bf(oc[4 * i + 6], oc[4 * i + 7]));
    asm volatile("fence.proxy.async.shared::cta;" ::: "memory");
    __syncwarp();
    e_store2d(&mout, ot + hf * 2048, (hp & 3) * 128 + hf * 64, (rt * 4 + (hp >> 2)) * 64 + w * 16);
  }
  asm volatile(ELECT "cp.async.bulk.commit_group;\n@p cp.async.bulk.wait_group.read 0;\n}\n" ::: "memory");
  TS(wg * 16 + 11);
  GT(61 + wg);
  if (w == 0) TSDUMP(0);
  if (w == 1) TSDUMP(48);
}

typedef CUresult (*EncodeFn)(CUtensorMap*, CUtensorMapDataType, cuuint32_t, void*, const cuuint64_t*, const cuuint64_t*,
                             const cuuint32_t*, const cuuint32_t*, CUtensorMapInterleave, CUtensorMapSwizzle,
                             CUtensorMapL2promotion, CUtensorMapFloatOOBfill);

}

extern "C" void kernel_launch(void* const* d_in, const int* in_sizes, int n_in, void* d_out, int out_size) {
  (void)in_sizes; (void)n_in; (void)out_size;
  void* fn = nullptr;
  cudaDriverEntryPointQueryResult qr;
  cudaGetDriverEntryPoint("cuTensorMapEncodeTiled", &fn, cudaEnableDefault, &qr);
  EncodeFn enc = (EncodeFn)fn;
  CUtensorMap mx, mw, mo, mu, mout, mw4;
  const cuuint32_t es[5] = {1, 1, 1, 1, 1};
  {
    cuuint64_t dims[2] = {512, 2048}, st[1] = {1024};
    cuuint32_t box[2] = {64, 128};
    enc(&mx, CU_TENSOR_MAP_DATA_TYPE_BFLOAT16, 2, d_in[0], dims, st, box, es, CU_TENSOR_MAP_INTERLEAVE_NONE,
        CU_TENSOR_MAP_SWIZZLE_128B, CU_TENSOR_MAP_L2_PROMOTION_L2_128B, CU_TENSOR_MAP_FLOAT_OOB_FILL_NONE);
  }
  {
    cuuint64_t dims[3] = {512, 512, 3}, st[2] = {3072, 1024};
    cuuint32_t box[3] = {32, 64, 3};
    enc(&mw, CU_TENSOR_MAP_DATA_TYPE_BFLOAT16, 3, d_in[1], dims, st, box, es, CU_TENSOR_MAP_INTERLEAVE_NONE,
        CU_TENSOR_MAP_SWIZZLE_64B, CU_TENSOR_MAP_L2_PROMOTION_L2_128B, CU_TENSOR_MAP_FLOAT_OOB_FILL_NONE);
  }
  {
    cuuint64_t dims[3] = {64, 512, 8}, st[2] = {1024, 128};
    cuuint32_t box[3] = {64, 64, 2};
    enc(&mo, CU_TENSOR_MAP_DATA_TYPE_BFLOAT16, 3, d_in[3], dims, st, box, es, CU_TENSOR_MAP_INTERLEAVE_NONE,
        CU_TENSOR_MAP_SWIZZLE_128B, CU_TENSOR_MAP_L2_PROMOTION_L2_128B, CU_TENSOR_MAP_FLOAT_OOB_FILL_NONE);
  }
  {
    cuuint64_t dims[4] = {512, 4, 16, 32}, st[3] = {16384, 1024, 65536};
    cuuint32_t box[4] = {64, 4, 16, 2};
    enc(&mu, CU_TENSOR_MAP_DATA_TYPE_BFLOAT16, 4, d_in[4], dims, st, box, es, CU_TENSOR_MAP_INTERLEAVE_NONE,
        CU_TENSOR_MAP_SWIZZLE_128B, CU_TENSOR_MAP_L2_PROMOTION_L2_128B, CU_TENSOR_MAP_FLOAT_OOB_FILL_NONE);
  }
  {
    cuuint64_t dims[2] = {1024, 2048}, st[1] = {2048};
    cuuint32_t box[2] = {64, 16};
    enc(&mout, CU_TENSOR_MAP_DATA_TYPE_BFLOAT16, 2, d_out, dims, st, box, es, CU_TENSOR_MAP_INTERLEAVE_NONE,
        CU_TENSOR_MAP_SWIZZLE_128B, CU_TENSOR_MAP_L2_PROMOTION_NONE, CU_TENSOR_MAP_FLOAT_OOB_FILL_NONE);
  }
  {
    cuuint64_t dims[4] = {512, 64, 3, 8}, st[3] = {3072, 1024, 64 * 3072};
    cuuint32_t box[4] = {32, 64, 3, 2};
    enc(&mw4, CU_TENSOR_MAP_DATA_TYPE_BFLOAT16, 4, d_in[1], dims, st, box, es, CU_TENSOR_MAP_INTERLEAVE_NONE,
        CU_TENSOR_MAP_SWIZZLE_64B, CU_TENSOR_MAP_L2_PROMOTION_L2_128B, CU_TENSOR_MAP_FLOAT_OOB_FILL_NONE);
  }
  Params P;
  P.x = (const __nv_bfloat16*)d_in[0];
  P.wphi = (const __nv_bfloat16*)d_in[2];
  P.wo = (const __nv_bfloat16*)d_in[3];
  P.logA = (const __nv_bfloat16*)d_in[5];
  P.Aim = (const __nv_bfloat16*)d_in[6];
  P.Cre = (const __nv_bfloat16*)d_in[7];
  P.Cim = (const __nv_bfloat16*)d_in[8];
  P.logdt = (const __nv_bfloat16*)d_in[9];
  P.Dskip = (const __nv_bfloat16*)d_in[10];
  P.out = (__nv_bfloat16*)d_out;
  cudaGetSymbolAddress((void**)&P.xs, g_x);
  P.ts = nullptr;
  cudaFuncSetAttribute(fused_kernel, cudaFuncAttributeMaxDynamicSharedMemorySize, SMEM_BYTES);
  fused_kernel<<<NCTA, NTHREADS, SMEM_BYTES>>>(P, mx, mw, mo, mu, mout, mw4);
}
```

```cpp
#include <cuda_runtime.h>
#include <cuda_bf16.h>
#include <cuda_fp16.h>
#include <cuda.h>
#include <stdint.h>

#define DBG_TS 0

namespace {

constexpr int NTHREADS = 512;
constexpr int NCTA = 128;
constexpr int OFF_W = 0;
constexpr int OFF_X = 98304;
constexpr int OFF_U = OFF_X + 65536;
constexpr int U_CH = 4416, U_ODD = 2240, U_PAD = 128;
constexpr int OFF_STG0 = OFF_U + 18432;
constexpr int SLAB = 3328;
constexpr int OFF_T = OFF_STG0 + 8 * SLAB;
constexpr int T_CH = 5216;
constexpr int T_D = 0;
constexpr int T_5 = 2144;
constexpr int T_3 = T_5 + 384;
constexpr int T_7 = T_5 + 1024;
constexpr int T_9 = T_7 + 320;
constexpr int T_KC = T_9 + 320;
constexpr int T_ST = T_5 - 1024;
constexpr int OFF_PHI = OFF_T + 4 * T_CH;
constexpr int OFF_EYE = OFF_PHI + 1024, OFF_ONE = OFF_EYE + 512;
constexpr int OFF_BAR = OFF_ONE + 256;
constexpr int SMEM_BYTES = OFF_BAR + 512 + 256 * DBG_TS;
constexpr uint32_t SB = 1024;
static_assert(T_KC + 2 * 656 <= T_CH, "table size");
static_assert(SMEM_BYTES <= 232448, "smem");
constexpr int MB_URAW = 0, MB_FULL = 1  , MB_WO = 17, MB_UFULL = 18, MB_OA = 19, MB_OB = 20, MB_OC = 21,
              MB_EMPTY = 22  , MB_AUX = 38;
__host__ __device__ constexpr uint32_t BAR(int i) { return SB + OFF_BAR + 8 * i; }
constexpr int NB_WG0 = 1, NB_ODONE = 2, NB_ST0 = 3  , NB_KV = 5, NB_YZ = 6, NB_INIT = 7, NB_PREP = 8, NB_PROD = 9, NB_KREAD = 10, NB_BDONE = 11, NB_GATE = 12,
              NB_Y = 7  ;
#define X2_AT -1
#define GATE_B 0
#define U_AT 2
#define ZERO_STEP 12
constexpr int SPIN_MAX = 1 << 16;

constexpr int X_CNT = 0;
constexpr int X_PART = 256;
constexpr int X_O = X_PART + 16 * 8 * 144;
constexpr int X_Y = X_O + 32 * 32 * 128;
constexpr int X_UT = X_Y + 512 * 8 * 32;
constexpr int X_SIZE = X_UT + 512 * (U_CH / 16);
__device__ __align__(128) uint4 g_x[X_SIZE];
extern __shared__ uint8_t smem_raw[];
#define TS(i) do {} while (0)
#define TS1(i) do {} while (0)
#define GT(i) do {} while (0)
#define TSDUMP(base) do {} while (0)

__device__ __forceinline__ uint32_t smem_u32(const void* p) { return (uint32_t)__cvta_generic_to_shared(p); }
__device__ __forceinline__ void mbar_arrive(uint32_t b) {
  asm volatile("mbarrier.arrive.shared::cta.b64 _, [%0];" ::"r"(b) : "memory");
}
__device__ __forceinline__ void mbar_wait(uint32_t b) {
  uint32_t done = 0;
#pragma unroll 1
  for (int i = 0; i < SPIN_MAX && !done; i++) {
    asm volatile("{\n.reg .pred p;\nmbarrier.try_wait.parity.shared::cta.b64 p, [%1], 0, 4000;\nselp.u32 %0, 1, 0, p;\n}\n"
                 : "=r"(done) : "r"(b) : "memory");
  }
}
__device__ __forceinline__ void mbar_spin(uint32_t b) {
  uint32_t done = 0;
#pragma unroll 1
  for (int i = 0; i < (SPIN_MAX << 4) && !done; i++) {
    asm volatile("{\n.reg .pred p;\nmbarrier.try_wait.parity.shared::cta.b64 p, [%1], 0;\nselp.u32 %0, 1, 0, p;\n}\n"
                 : "=r"(done) : "r"(b) : "memory");
  }
}
__device__ __forceinline__ void mbar_init(uint32_t b, int n) {
  asm volatile("mbarrier.init.shared::cta.b64 [%0], %1;" ::"r"(b), "r"(n) : "memory");
}
__device__ __forceinline__ void mbar_expect(uint32_t b, int bytes) {
  asm volatile("mbarrier.arrive.expect_tx.shared::cta.b64 _, [%0], %1;" ::"r"(b), "r"(bytes) : "memory");
}
__device__ __forceinline__ void nb_sync(int id, int n) { asm volatile("bar.sync %0, %1;" ::"r"(id), "r"(n) : "memory"); }
__device__ __forceinline__ void nb_arrive(int id, int n) { asm volatile("bar.arrive %0, %1;" ::"r"(id), "r"(n) : "memory"); }
#define ELECT "{\n.reg .pred p;\nelect.sync _|p, 0xffffffff;\n@p "
__device__ __forceinline__ void e_arrive(uint32_t b) {
  asm volatile(ELECT "mbarrier.arrive.shared::cta.b64 _, [%0];\n}\n" ::"r"(b) : "memory");
}
__device__ __forceinline__ void e_expect(uint32_t b, int bytes) {
  asm volatile(ELECT "mbarrier.arrive.expect_tx.shared::cta.b64 _, [%0], %1;\n}\n" ::"r"(b), "r"(bytes) : "memory");
}
__device__ __forceinline__ void e_tma2d(uint32_t dst, const CUtensorMap* m, uint32_t bar, int c0, int c1) {
  asm volatile(ELECT "cp.async.bulk.tensor.2d.shared::cluster.global.mbarrier::complete_tx::bytes [%0], [%1, {%3,%4}], [%2];\n}\n"
               ::"r"(dst), "l"(m), "r"(bar), "r"(c0), "r"(c1) : "memory");
}
__device__ __forceinline__ void e_tma3d(uint32_t dst, const CUtensorMap* m, uint32_t bar, int c0, int c1, int c2) {
  asm volatile(ELECT "cp.async.bulk.tensor.3d.shared::cluster.global.mbarrier::complete_tx::bytes [%0], [%1, {%3,%4,%5}], [%2];\n}\n"
               ::"r"(dst), "l"(m), "r"(bar), "r"(c0), "r"(c1), "r"(c2) : "memory");
}
__device__ __forceinline__ void e_tma4d(uint32_t dst, const CUtensorMap* m, uint32_t bar, int c0, int c3) {
  asm volatile(ELECT "cp.async.bulk.tensor.4d.shared::cluster.global.mbarrier::complete_tx::bytes [%0], [%1, {%3,%5,%5,%4}], [%2];\n}\n"
               ::"r"(dst), "l"(m), "r"(bar), "r"(c0), "r"(c3), "r"(0) : "memory");
}
__device__ __forceinline__ void e_bulk(uint32_t dst, const void* src, int bytes, uint32_t bar) {
  asm volatile(ELECT "cp.async.bulk.shared::cluster.global.mbarrier::complete_tx::bytes [%0], [%1], %2, [%3];\n}\n"
               ::"r"(dst), "l"(src), "r"(bytes), "r"(bar) : "memory");
}
__device__ __forceinline__ void e_prefetch(const void* p, int bytes) {
  asm volatile(ELECT "cp.async.bulk.prefetch.L2.global [%0], %1;\n}\n" ::"l"(p), "r"(bytes) : "memory");
}
__device__ __forceinline__ void e_store2d(const CUtensorMap* m, uint32_t src, int c0, int c1) {
  asm volatile(ELECT "cp.async.bulk.tensor.2d.global.shared::cta.bulk_group [%0, {%2,%3}], [%1];\n}\n"
               ::"l"(m), "r"(src), "r"(c0), "r"(c1) : "memory");
}
__host__ __device__ constexpr uint64_t mkdesc(uint32_t addr, uint32_t lbo, uint32_t sbo, int swz) {
  return (uint64_t)((addr & 0x3FFFF) >> 4) | ((uint64_t)(lbo >> 4) << 16) | ((uint64_t)(sbo >> 4) << 32) |
         ((uint64_t)swz << 62);
}
#define SPLIT() asm volatile("{\n.reg .pred p;\nsetp.eq.u32 p, %0, %1;\n@p exit;\n}\n" ::"r"(blockIdx.y), "n"(__LINE__) : "memory")
#define WG_FENCE() asm volatile("wgmma.fence.sync.aligned;" ::: "memory")
#define WG_COMMIT() asm volatile("wgmma.commit_group.sync.aligned;" ::: "memory")
#define WG_WAIT(n) asm volatile("wgmma.wait_group.sync.aligned " #n ";" ::: "memory")

__device__ __forceinline__ void mma(float& d0, float& d1, float& d2, float& d3, uint32_t a0, uint32_t a1, uint32_t a2,
                                    uint32_t a3, uint32_t b0, uint32_t b1) {
  asm volatile("mma.sync.aligned.m16n8k16.row.col.f32.bf16.bf16.f32 {%0,%1,%2,%3},{%4,%5,%6,%7},{%8,%9},{%0,%1,%2,%3};"
               : "+f"(d0), "+f"(d1), "+f"(d2), "+f"(d3)
               : "r"(a0), "r"(a1), "r"(a2), "r"(a3), "r"(b0), "r"(b1));
}
__device__ __forceinline__ void mmac(float (&d)[4], uint32_t a0, uint32_t a1, uint32_t a2, uint32_t a3, uint32_t b0,
                                     uint32_t b1, const float (&c)[4]) {
  asm volatile("mma.sync.aligned.m16n8k16.row.col.f32.bf16.bf16.f32 {%0,%1,%2,%3},{%4,%5,%6,%7},{%8,%9},{%10,%11,%12,%13};"
               : "=f"(d[0]), "=f"(d[1]), "=f"(d[2]), "=f"(d[3])
               : "r"(a0), "r"(a1), "r"(a2), "r"(a3), "r"(b0), "r"(b1), "f"(c[0]), "f"(c[1]), "f"(c[2]), "f"(c[3]));
}
__device__ __forceinline__ void mma_p(int p, float (&d)[4], uint32_t a0, uint32_t a1, uint32_t a2, uint32_t a3, uint32_t b0, uint32_t b1) {
  asm volatile("{\n.reg .pred q;\nsetp.ne.b32 q, %10, 0;\n"
               "@q mma.sync.aligned.m16n8k16.row.col.f32.bf16.bf16.f32 {%0,%1,%2,%3},{%4,%5,%6,%7},{%8,%9},{%0,%1,%2,%3};\n}\n"
               : "+f"(d[0]), "+f"(d[1]), "+f"(d[2]), "+f"(d[3])
               : "r"(a0), "r"(a1), "r"(a2), "r"(a3), "r"(b0), "r"(b1), "r"(p));
}
__device__ __forceinline__ void mmac_p(int p, float (&d)[4], uint32_t a0, uint32_t a1, uint32_t a2, uint32_t a3, uint32_t b0,
                                       uint32_t b1, const float (&c)[4]) {
  asm volatile("{\n.reg .pred q;\nsetp.ne.b32 q, %14, 0;\n"
               "@q mma.sync.aligned.m16n8k16.row.col.f32.bf16.bf16.f32 {%0,%1,%2,%3},{%4,%5,%6,%7},{%8,%9},{%10,%11,%12,%13};\n}\n"
               : "+f"(d[0]), "+f"(d[1]), "+f"(d[2]), "+f"(d[3])
               : "r"(a0), "r"(a1), "r"(a2), "r"(a3), "r"(b0), "r"(b1), "f"(c[0]), "f"(c[1]), "f"(c[2]), "f"(c[3]), "r"(p));
}
__device__ __forceinline__ void mma_h(float (&d)[4], const uint32_t (&a)[4], uint32_t b0, uint32_t b1) {
  asm volatile("mma.sync.aligned.m16n8k16.row.col.f32.f16.f16.f32 {%0,%1,%2,%3},{%4,%5,%6,%7},{%8,%9},{%0,%1,%2,%3};"
               : "+f"(d[0]), "+f"(d[1]), "+f"(d[2]), "+f"(d[3]) : "r"(a[0]), "r"(a[1]), "r"(a[2]), "r"(a[3]), "r"(b0), "r"(b1));
}
__device__ __forceinline__ void mma0(float& d0, float& d1, float& d2, float& d3, uint32_t a0, uint32_t a1, uint32_t a2,
                                     uint32_t a3, uint32_t b0, uint32_t b1) {
  asm volatile("mma.sync.aligned.m16n8k16.row.col.f32.bf16.bf16.f32 {%0,%1,%2,%3},{%4,%5,%6,%7},{%8,%9},{%10,%10,%10,%10};"
               : "=f"(d0), "=f"(d1), "=f"(d2), "=f"(d3)
               : "r"(a0), "r"(a1), "r"(a2), "r"(a3), "r"(b0), "r"(b1), "f"(0.f));
}
__device__ __forceinline__ uint32_t pack_bf(float lo, float hi) {
  uint32_t r;
  asm("cvt.rn.bf16x2.f32 %0, %1, %2;" : "=r"(r) : "f"(hi), "f"(lo));
  return r;
}
__device__ __forceinline__ float bf_lo(uint32_t w) { return __uint_as_float(w << 16); }
__device__ __forceinline__ float bf_hi(uint32_t w) { return __uint_as_float(w & 0xffff0000u); }
__device__ __forceinline__ float bf_round(float x) { return __bfloat162float(__float2bfloat16_rn(x)); }
__device__ __forceinline__ uint32_t bmax2(uint32_t a, uint32_t b) {
  uint32_t r; asm("max.bf16x2 %0, %1, %2;" : "=r"(r) : "r"(a), "r"(b)); return r;
}
__device__ __forceinline__ uint32_t bmin2(uint32_t a, uint32_t b) {
  uint32_t r; asm("min.bf16x2 %0, %1, %2;" : "=r"(r) : "r"(a), "r"(b)); return r;
}
__device__ __forceinline__ float ex2(float x) { float r; asm("ex2.approx.ftz.f32 %0, %1;" : "=f"(r) : "f"(x)); return r; }
__device__ __forceinline__ float rcp(float x) { float r; asm("rcp.approx.ftz.f32 %0, %1;" : "=f"(r) : "f"(x)); return r; }
__device__ __forceinline__ void ldsm4(uint32_t (&r)[4], uint32_t a) {
  asm volatile("ldmatrix.sync.aligned.m8n8.x4.shared.b16 {%0,%1,%2,%3}, [%4];"
               : "=r"(r[0]), "=r"(r[1]), "=r"(r[2]), "=r"(r[3]) : "r"(a) : "memory");
}
__device__ __forceinline__ void ldsm4t(uint32_t (&r)[4], uint32_t a) {
  asm volatile("ldmatrix.sync.aligned.m8n8.x4.trans.shared.b16 {%0,%1,%2,%3}, [%4];"
               : "=r"(r[0]), "=r"(r[1]), "=r"(r[2]), "=r"(r[3]) : "r"(a) : "memory");
}
__device__ __forceinline__ void stsm4(uint32_t a, uint32_t r0, uint32_t r1, uint32_t r2, uint32_t r3) {
  asm volatile("stmatrix.sync.aligned.m8n8.x4.shared.b16 [%0], {%1,%2,%3,%4};"
               ::"r"(a), "r"(r0), "r"(r1), "r"(r2), "r"(r3) : "memory");
}
__device__ __forceinline__ uint32_t lds32(uint32_t a) {
  uint32_t r; asm volatile("ld.shared.u32 %0, [%1];" : "=r"(r) : "r"(a) : "memory"); return r;
}
__device__ __forceinline__ uint32_t lds16(uint32_t a) {
  uint32_t r; asm volatile("{\n.reg .u16 h;\nld.shared.u16 h, [%1];\ncvt.u32.u16 %0, h;\n}\n" : "=r"(r) : "r"(a) : "memory"); return r;
}
__device__ __forceinline__ uint2 lds64(uint32_t a) {
  uint2 r; asm volatile("ld.shared.v2.u32 {%0,%1}, [%2];" : "=r"(r.x), "=r"(r.y) : "r"(a) : "memory"); return r;
}
__device__ __forceinline__ uint4 lds128(uint32_t a) {
  uint4 r;
  asm volatile("ld.shared.v4.u32 {%0,%1,%2,%3}, [%4];" : "=r"(r.x), "=r"(r.y), "=r"(r.z), "=r"(r.w) : "r"(a) : "memory");
  return r;
}
__device__ __forceinline__ void sts32(uint32_t a, uint32_t v) { asm volatile("st.shared.u32 [%0], %1;" ::"r"(a), "r"(v) : "memory"); }
__device__ __forceinline__ void sts16(uint32_t a, uint32_t v) {
  asm volatile("{\n.reg .u16 h;\ncvt.u16.u32 h, %1;\nst.shared.u16 [%0], h;\n}\n" ::"r"(a), "r"(v) : "memory");
}
__device__ __forceinline__ void sts64(uint32_t a, uint32_t x, uint32_t y) {
  asm volatile("st.shared.v2.u32 [%0], {%1,%2};" ::"r"(a), "r"(x), "r"(y) : "memory");
}
__device__ __forceinline__ void sts128(uint32_t a, uint32_t x, uint32_t y, uint32_t z, uint32_t w) {
  asm volatile("st.shared.v4.u32 [%0], {%1,%2,%3,%4};" ::"r"(a), "r"(x), "r"(y), "r"(z), "r"(w) : "memory");
}
__device__ __forceinline__ uint4 ld_x(const uint4* p) {
  uint4 r;
  asm volatile("{\n.reg .b128 t;\nld.relaxed.gpu.global.b128 t, [%4];\nmov.b128 {%0,%1,%2,%3}, t;\n}\n"
               : "=r"(r.x), "=r"(r.y), "=r"(r.z), "=r"(r.w) : "l"(p) : "memory");
  return r;
}
__device__ __forceinline__ uint32_t ld_x32(const uint32_t* p) {
  uint32_t r; asm volatile("ld.relaxed.gpu.global.u32 %0, [%1];" : "=r"(r) : "l"(p) : "memory"); return r;
}
__device__ __forceinline__ void st_x(uint4* p, uint32_t x, uint32_t y, uint32_t z, uint32_t w) {
  asm volatile("{\n.reg .b128 t;\nmov.b128 t, {%1,%2,%3,%4};\nst.relaxed.gpu.global.b128 [%0], t;\n}\n"
               ::"l"(p), "r"(x), "r"(y), "r"(z), "r"(w) : "memory");
}
__device__ __forceinline__ void st_x_p(int p, uint4* a, uint32_t x, uint32_t y, uint32_t z, uint32_t w) {
  asm volatile("{\n.reg .b128 t;\n.reg .pred q;\nsetp.ne.b32 q, %5, 0;\nmov.b128 t, {%1,%2,%3,%4};\n@q st.relaxed.gpu.global.b128 [%0], t;\n}\n"
               ::"l"(a), "r"(x), "r"(y), "r"(z), "r"(w), "r"(p) : "memory");
}
__device__ __forceinline__ void sts64_p(int p, uint32_t a, uint32_t x, uint32_t y) {
  asm volatile("{\n.reg .pred q;\nsetp.ne.b32 q, %3, 0;\n@q st.shared.v2.u32 [%0], {%1,%2};\n}\n" ::"r"(a), "r"(x), "r"(y), "r"(p) : "memory");
}
__device__ __forceinline__ void st_x32(uint32_t* p, uint32_t x) {
  asm volatile("st.relaxed.gpu.global.u32 [%0], %1;" ::"l"(p), "r"(x) : "memory");
}
__device__ __forceinline__ uint32_t nz(uint32_t w) { return max(w, 1u); }
__device__ __forceinline__ uint32_t fu(float x) { return __float_as_uint(x); }
__device__ __forceinline__ float uf(uint32_t x) { return __uint_as_float(x); }

__device__ __forceinline__ void wgmma_ss_n96(float (&d)[48], uint64_t da, uint64_t db, int sc) {
  asm volatile("{\n.reg .pred p;\nsetp.ne.b32 p, %50, 0;\n"
      "wgmma.mma_async.sync.aligned.m64n96k16.f32.bf16.bf16 "
      "{%0,%1,%2,%3,%4,%5,%6,%7,%8,%9,%10,%11,%12,%13,%14,%15,%16,%17,%18,%19,%20,%21,%22,%23,%24,%25,%26,%27,%28,%29,%30,%31,%32,%33,%34,%35,%36,%37,%38,%39,%40,%41,%42,%43,%44,%45,%46,%47}, "
      "%48, %49, p, 1, 1, 0, 1;\n}\n"
      : "+f"(d[0]), "+f"(d[1]), "+f"(d[2]), "+f"(d[3]), "+f"(d[4]), "+f"(d[5]), "+f"(d[6]), "+f"(d[7]),
        "+f"(d[8]), "+f"(d[9]), "+f"(d[10]), "+f"(d[11]), "+f"(d[12]), "+f"(d[13]), "+f"(d[14]), "+f"(d[15]),
        "+f"(d[16]), "+f"(d[17]), "+f"(d[18]), "+f"(d[19]), "+f"(d[20]), "+f"(d[21]), "+f"(d[22]), "+f"(d[23]),
        "+f"(d[24]), "+f"(d[25]), "+f"(d[26]), "+f"(d[27]), "+f"(d[28]), "+f"(d[29]), "+f"(d[30]), "+f"(d[31]),
        "+f"(d[32]), "+f"(d[33]), "+f"(d[34]), "+f"(d[35]), "+f"(d[36]), "+f"(d[37]), "+f"(d[38]), "+f"(d[39]),
        "+f"(d[40]), "+f"(d[41]), "+f"(d[42]), "+f"(d[43]), "+f"(d[44]), "+f"(d[45]), "+f"(d[46]), "+f"(d[47])
      : "l"(da), "l"(db), "r"(sc));
}

__device__ __forceinline__ void wgmma_ss_n128(float (&d)[64], uint64_t da, uint64_t db, int sc) {
  asm volatile("{\n.reg .pred p;\nsetp.ne.b32 p, %66, 0;\n"
      "wgmma.mma_async.sync.aligned.m64n128k16.f32.bf16.bf16 "
      "{%0,%1,%2,%3,%4,%5,%6,%7,%8,%9,%10,%11,%12,%13,%14,%15,%16,%17,%18,%19,%20,%21,%22,%23,%24,%25,%26,%27,%28,%29,%30,%31,%32,%33,%34,%35,%36,%37,%38,%39,%40,%41,%42,%43,%44,%45,%46,%47,%48,%49,%50,%51,%52,%53,%54,%55,%56,%57,%58,%59,%60,%61,%62,%63}, "
      "%64, %65, p, 1, 1, 0, 1;\n}\n"
      : "+f"(d[0]), "+f"(d[1]), "+f"(d[2]), "+f"(d[3]), "+f"(d[4]), "+f"(d[5]), "+f"(d[6]), "+f"(d[7]),
        "+f"(d[8]), "+f"(d[9]), "+f"(d[10]), "+f"(d[11]), "+f"(d[12]), "+f"(d[13]), "+f"(d[14]), "+f"(d[15]),
        "+f"(d[16]), "+f"(d[17]), "+f"(d[18]), "+f"(d[19]), "+f"(d[20]), "+f"(d[21]), "+f"(d[22]), "+f"(d[23]),
        "+f"(d[24]), "+f"(d[25]), "+f"(d[26]), "+f"(d[27]), "+f"(d[28]), "+f"(d[29]), "+f"(d[30]), "+f"(d[31]),
        "+f"(d[32]), "+f"(d[33]), "+f"(d[34]), "+f"(d[35]), "+f"(d[36]), "+f"(d[37]), "+f"(d[38]), "+f"(d[39]),
        "+f"(d[40]), "+f"(d[41]), "+f"(d[42]), "+f"(d[43]), "+f"(d[44]), "+f"(d[45]), "+f"(d[46]), "+f"(d[47]),
        "+f"(d[48]), "+f"(d[49]), "+f"(d[50]), "+f"(d[51]), "+f"(d[52]), "+f"(d[53]), "+f"(d[54]), "+f"(d[55]),
        "+f"(d[56]), "+f"(d[57]), "+f"(d[58]), "+f"(d[59]), "+f"(d[60]), "+f"(d[61]), "+f"(d[62]), "+f"(d[63])
      : "l"(da), "l"(db), "r"(sc));
}

__device__ __forceinline__ void wgmma_ss_n40(float (&d)[20], uint64_t da, uint64_t db, int sc) {
  asm volatile("{\n.reg .pred p;\nsetp.ne.b32 p, %22, 0;\n"
      "wgmma.mma_async.sync.aligned.m64n40k16.f32.bf16.bf16 "
      "{%0,%1,%2,%3,%4,%5,%6,%7,%8,%9,%10,%11,%12,%13,%14,%15,%16,%17,%18,%19}, "
      "%20, %21, p, 1, 1, 1, 1;\n}\n"
      : "+f"(d[0]), "+f"(d[1]), "+f"(d[2]), "+f"(d[3]), "+f"(d[4]), "+f"(d[5]), "+f"(d[6]), "+f"(d[7]),
        "+f"(d[8]), "+f"(d[9]), "+f"(d[10]), "+f"(d[11]), "+f"(d[12]), "+f"(d[13]), "+f"(d[14]), "+f"(d[15]),
        "+f"(d[16]), "+f"(d[17]), "+f"(d[18]), "+f"(d[19])
      : "l"(da), "l"(db), "r"(sc));
}

__device__ __forceinline__ void wgmma_rs_n8(float (&d)[4], const uint4& a, uint64_t db, int sc) {
  asm volatile("{\n.reg .pred p;\nsetp.ne.b32 p, %9, 0;\n"
      "wgmma.mma_async.sync.aligned.m64n8k16.f32.bf16.bf16 "
      "{%0,%1,%2,%3}, "
      "{%4,%5,%6,%7}, %8, p, 1, 1, 1;\n}\n"
      : "+f"(d[0]), "+f"(d[1]), "+f"(d[2]), "+f"(d[3])
      : "r"(a.x), "r"(a.y), "r"(a.z), "r"(a.w), "l"(db), "r"(sc));
}

__device__ __forceinline__ void wgmma_rs_n16(float (&d)[8], const uint4& a, uint64_t db, int sc) {
  asm volatile("{\n.reg .pred p;\nsetp.ne.b32 p, %13, 0;\n"
      "wgmma.mma_async.sync.aligned.m64n16k16.f32.bf16.bf16 "
      "{%0,%1,%2,%3,%4,%5,%6,%7}, "
      "{%8,%9,%10,%11}, %12, p, 1, 1, 1;\n}\n"
      : "+f"(d[0]), "+f"(d[1]), "+f"(d[2]), "+f"(d[3]), "+f"(d[4]), "+f"(d[5]), "+f"(d[6]), "+f"(d[7])
      : "r"(a.x), "r"(a.y), "r"(a.z), "r"(a.w), "l"(db), "r"(sc));
}

__device__ __forceinline__ void wgmma_rs_n24(float (&d)[12], const uint4& a, uint64_t db, int sc) {
  asm volatile("{\n.reg .pred p;\nsetp.ne.b32 p, %17, 0;\n"
      "wgmma.mma_async.sync.aligned.m64n24k16.f32.bf16.bf16 "
      "{%0,%1,%2,%3,%4,%5,%6,%7,%8,%9,%10,%11}, "
      "{%12,%13,%14,%15}, %16, p, 1, 1, 1;\n}\n"
      : "+f"(d[0]), "+f"(d[1]), "+f"(d[2]), "+f"(d[3]), "+f"(d[4]), "+f"(d[5]), "+f"(d[6]), "+f"(d[7]),
        "+f"(d[8]), "+f"(d[9]), "+f"(d[10]), "+f"(d[11])
      : "r"(a.x), "r"(a.y), "r"(a.z), "r"(a.w), "l"(db), "r"(sc));
}

struct Params {
  const __nv_bfloat16 *logA, *Aim, *Cre, *Cim, *logdt, *Dskip, *x, *wphi, *wo;
  __nv_bfloat16* out;
  uint4* xs;
  long long* ts;
};

__device__ __forceinline__ uint4 tr_row(const uint4 (&v)[8], int i) {
  uint32_t o[4];
#pragma unroll
  for (int m = 0; m < 4; m++) {
    const uint4 &ra = v[2 * m], &rb = v[2 * m + 1];
    const int k = i >> 1;
    const uint32_t xa = k == 0 ? ra.x : k == 1 ? ra.y : k == 2 ? ra.z : ra.w;
    const uint32_t xb = k == 0 ? rb.x : k == 1 ? rb.y : k == 2 ? rb.z : rb.w;
    o[m] = __byte_perm(xa, xb, (i & 1) ? 0x7632 : 0x5410);
  }
  return make_uint4(o[0], o[1], o[2], o[3]);
}

struct cpx { float r, i; };
__device__ __forceinline__ cpx csq(cpx a) { return {a.r * a.r - a.i * a.i, 2.f * (a.r * a.i)}; }
__device__ __forceinline__ cpx polar(float e, float t) {
  const float m = ex2(e);
  return {m * __cosf(t), m * __sinf(t)};
}

struct KgenRaw { unsigned short la, ai, cr, ci, ldt; };
__device__ __forceinline__ KgenRaw kgen_load(const Params& P, int d, int unit, int lane) {
  const int o = d * 128 + unit * 32 + lane;
  return {__ldg((const unsigned short*)P.logA + o), __ldg((const unsigned short*)P.Aim + o), __ldg((const unsigned short*)P.Cre + o),
          __ldg((const unsigned short*)P.Cim + o), __ldg((const unsigned short*)P.logdt + d)};
}
struct hmul { __half2 a, b; };
__device__ __forceinline__ hmul mk_mul(cpx w) {
  uint32_t b;
  asm("{\n.reg .f32 n;\nneg.ftz.f32 n, %1;\ncvt.rn.f16x2.f32 %0, %2, n;\n}\n" : "=r"(b) : "f"(w.i), "f"(w.r));
  return {__floats2half2_rn(w.r, w.i), *(const __half2*)&b};
}
__device__ __forceinline__ __half2 hcm(__half2 z, const hmul& w) { return __hfma2(__high2half2(z), w.b, __hmul2(__low2half2(z), w.a)); }
__device__ __forceinline__ uint32_t hu(__half2 v) { return *(const uint32_t*)&v; }

struct KgenAddr { uint32_t sa, sb, lb, lc, la; };
__device__ __forceinline__ KgenAddr kgen_addr(int lane, uint32_t buf) {
  KgenAddr a;
  a.sa = buf + (lane & 7) * 128 + ((((lane >> 3) ^ lane) & 7) << 4);
  a.lb = buf + (lane >> 3) * 128 + (((lane ^ (lane >> 3)) & 7) << 4);
  a.la = buf + ((lane >> 3) & 1) * 1024 + (lane >> 4) * 128 + (((lane ^ (lane >> 4)) & 7) << 4);
  a.sb = a.sa ^ 64; a.lc = a.lb ^ 64;
  asm volatile("" : "+r"(a.sa), "+r"(a.sb), "+r"(a.lb), "+r"(a.lc), "+r"(a.la));
  return a;
}
__device__ __forceinline__ void kgen_unit(const KgenRaw& r, const KgenAddr& ad, uint32_t zero, float (&k)[5][4], float& k2048, float& sc) {
  const float dt = bf_round(expf(bf_lo(r.ldt)));
  const float a2 = bf_round(ex2(bf_lo(r.la) * 1.4426950408889634f)) * (dt * -1.4426950408889634f);
  const float f = bf_lo(r.ai) * dt;
  const float r128 = f * 20.371832715762604f;
  const uint32_t ex = min(max(__reduce_max_sync(0xffffffffu, max(r.cr & 0x7fffu, r.ci & 0x7fffu)) >> 7, 1u), 253u);
  const float cs = uf((254u - ex) << 23);
  sc = 2.f * dt * uf(ex << 23);
  const cpx C = {bf_lo(r.cr) * cs, -bf_lo(r.ci) * cs};
  auto put = [&](const __half2 (&v)[8], uint32_t off) {
    stsm4(ad.sa + off, hu(v[0]), hu(v[1]), hu(v[2]), hu(v[3]));
    stsm4(ad.sb + off, hu(v[4]), hu(v[5]), hu(v[6]), hu(v[7]));
  };
  uint32_t A[4][4], B[5][2][4];
  auto get = [&](int j, uint32_t off) {
    __syncwarp();
    ldsm4(B[j][0], ad.lb + off);
    ldsm4(B[j][1], ad.lc + 512 + off);
  };
  auto tile = [&](int j) {
    k[j][0] = k[j][1] = k[j][2] = k[j][3] = 0.f;
#pragma unroll
    for (int s = 0; s < 4; s++) mma_h(k[j], A[s], B[j][s >> 1][2 * (s & 1)], B[j][s >> 1][2 * (s & 1) + 1]);
  };
  auto after = [&](cpx v, uint32_t dep) { return cpx{uf(fu(v.r) ^ (dep & zero)), v.i}; };
  const cpx w1 = polar(a2, f), w128 = polar(a2 * 128.f, (r128 - rintf(r128)) * 6.283185307179586f);
  const cpx w2 = csq(w1), w4 = csq(w2);
  __half2 t0[8], t1[8], t2[8], t3[8], t4[8];
  const hmul m2 = mk_mul(w2), m4 = mk_mul(w4), m128 = mk_mul(w128);
  t0[0] = __floats2half2_rn(1.f, 0.f); t0[1] = __floats2half2_rn(w1.r, w1.i); t0[2] = m2.a; t0[4] = m4.a;
  t0[3] = hcm(t0[1], m2); t0[5] = hcm(t0[1], m4); t0[6] = hcm(t0[2], m4); t0[7] = hcm(t0[3], m4);
  put(t0, 0); get(0, 0);
  t1[0] = m128.a;
#pragma unroll
  for (int i = 1; i < 8; i++) t1[i] = hcm(t0[i], m128);
  put(t1, 1024); get(1, 1024);
  {
    cpx w8 = csq(after(w4, B[0][0][0]));
    w8.i = -w8.i;
    const cpx w16 = csq(w8), w32 = csq(w16), w64 = csq(w32);
    const hmul m8 = mk_mul(w8), m16 = mk_mul(w16), m32 = mk_mul(w32), m64 = mk_mul(w64);
    __half2 a[8];
    a[0] = __floats2half2_rn(C.r, C.i); a[1] = hcm(a[0], m8);
    a[2] = hcm(a[0], m16); a[3] = hcm(a[1], m16);
#pragma unroll
    for (int i = 0; i < 4; i++) a[4 + i] = hcm(a[i], m32);
    put(a, 0);
#pragma unroll
    for (int i = 0; i < 8; i++) a[i] = hcm(a[i], m64);
    put(a, 1024);
    __syncwarp();
#pragma unroll
    for (int s = 0; s < 4; s++) ldsm4(A[s], (ad.la ^ (s << 5)) + s * 256);
  }
  const cpx w256 = csq(after(w128, B[1][0][0]));
  const hmul m256 = mk_mul(w256);
  t2[0] = m256.a;
#pragma unroll
  for (int i = 1; i < 8; i++) t2[i] = hcm((i & 1) ? t1[i & 6] : t0[i & 6], m256);
  put(t2, 0); get(2, 0);
  tile(0); tile(1);
  const cpx w512 = csq(after(w256, A[0][0]));
  const hmul m512 = mk_mul(w512);
  t3[0] = m512.a;
#pragma unroll
  for (int i = 1; i < 8; i++) t3[i] = hcm((i & 2) ? t2[i & 5] : ((i & 1) ? t1[i & 4] : t0[i & 4]), m512);
  put(t3, 1024); get(3, 1024);
  tile(2);
  const cpx w1024 = csq(after(w512, B[2][0][0])), we = csq(w1024);
  const hmul m1024 = mk_mul(w1024);
  t4[0] = m1024.a;
#pragma unroll
  for (int i = 1; i < 8; i++) t4[i] = hcm((i & 4) ? t3[i & 3] : ((i & 2) ? t2[i & 1] : t1[0]), m1024);
  put(t4, 0); get(4, 0);
  tile(3); tile(4);
  k2048 = (C.r * we.r + C.i * we.i) * sc;
}

__device__ __forceinline__ void build_tables(uint32_t tb, int lane, float (&k)[5][4], float k2048) {
  const int g = lane >> 2, c = lane & 3;
  const uint32_t kc = tb + T_KC + 16;
  {
    const uint32_t a0 = kc + 16 * g + 4 * c, a2 = kc + 2 * (256 + 4 * g + c);
    const uint32_t a3 = kc + 2 * (384 + 2 * g + 64 * (c & 1) + (c >> 1)), a4 = kc + 2 * (512 + g + 32 * c);
#pragma unroll
    for (int r = 0; r < 2; r++) {
      sts32(a0 + 128 * r, pack_bf(k[0][2 * r], k[0][2 * r + 1]));
      sts32(a0 + 128 * r + 256, pack_bf(k[1][2 * r], k[1][2 * r + 1]));
      const uint32_t w2 = pack_bf(k[2][2 * r], k[2][2 * r + 1]);
      const uint32_t w3 = pack_bf(k[3][2 * r], k[3][2 * r + 1]);
      const uint32_t w4 = pack_bf(k[4][2 * r], k[4][2 * r + 1]);
      sts16(a2 + 64 * r, w2); sts16(a2 + 64 * r + 128, w2 >> 16);
      sts16(a3 + 32 * r, w3); sts16(a3 + 32 * r + 64, w3 >> 16);
      sts16(a4 + 16 * r, w4); sts16(a4 + 16 * r + 32, w4 >> 16);
    }
  }
  if (lane == 0) { sts16(kc + 2 * 640, pack_bf(k2048, 0.f)); sts32(kc - 4, 0); }
  __syncwarp();
  const uint32_t td = tb + T_D + 32;
#pragma unroll
  for (int hf = 0; hf < 2; hf++) {
    const uint2 v = lds64(kc + 256 * hf + 8 * lane);
    const uint32_t pv = lds32(kc + 256 * hf + 8 * lane - 4);
    sts128(td + 512 * hf + 16 * lane, __byte_perm(v.x, pv, 0x7610), __byte_perm(v.x, v.x, 0x1032), __byte_perm(v.y, v.x, 0x7610),
           __byte_perm(v.y, v.y, 0x1032));
  }
#pragma unroll
  for (int hf = 0; hf < 2; hf++) {
    const uint32_t v = lds32(kc + 512 + 128 * hf + 4 * lane), nx = lds32(kc + 516 + 128 * hf + 4 * lane);
    uint32_t w0 = __byte_perm(v, v, 0x1010);
    const uint32_t w1 = w0;
    if (hf == 0) { const uint32_t pv = lds32(kc + 508); if (lane == 0) w0 = __byte_perm(v, pv, 0x7610); }
    sts128(td + 1024 + 512 * hf + 16 * lane, w0, w1, __byte_perm(v, v, 0x1032), __byte_perm(nx, v, 0x7610));
  }
  {
    const uint32_t kk = lds16(kc + 2 * 384);
    const uint32_t w = lane < 3 ? (kk | (kk << 16)) : (lane == 3 ? (kk << 16) : 0u);
    if (lane < 24) sts32(td + 4 * (lane < 16 ? 512 + lane : lane - 24), w);
    const uint32_t lo_ = lds16(kc + 2 * 511), le_ = lds16(kc + 2 * 512);
    const uint32_t ja = tb + T_5 + (lane < 16 ? 4 * lane : 256 + 4 * lane);
    sts32(ja, lane == 16 ? (le_ << 16) : 0u);
    sts32(ja + 384, lane == 16 ? (lo_ << 16) : 0u);
    sts32(tb + (lane < 16 ? T_7 : T_9 - 64) + 4 * lane, 0u);
  }
#pragma unroll
  for (int s = 0; s < 2; s++) {
    const uint32_t b = kc + 2 * (s ? 512 : 384) + 8 * lane;
    const uint2 v = lds64(b);
    uint32_t em = lds16(b - 2), e0 = v.x;
    const uint32_t e4 = lds16(b + 8);
    if (lane == 0) { em = 0; e0 = 0; }
    sts64(tb + (s ? T_7 : T_3) + 64 + 8 * lane, __byte_perm(v.x, em, 0x5432), __byte_perm(v.y, v.x, 0x7632));
    sts64(tb + (s ? T_9 : T_5) + 64 + 8 * lane, __byte_perm(v.y, e0, 0x5410), __byte_perm(e4, v.y, 0x5410));
  }
  __syncwarp();
}

__device__ __forceinline__ uint32_t box2w(int lo, int n, int o) {
  return ((unsigned)(o - lo) < (unsigned)n ? 0x3F80u : 0u) | ((unsigned)(o + 1 - lo) < (unsigned)n ? 0x3F800000u : 0u);
}

__device__ __forceinline__ void conv_channel(uint32_t ub, uint32_t tb, int lane, uint4* ydst) {
  const int g = lane >> 2, c = lane & 3, x = g - 2 * c;
  const int mi = lane >> 3;
  const uint32_t qa = ub + U_PAD + 16 * (lane & 7) + ((mi == 0 || mi == 3) ? U_ODD : 0) - (mi == 0 ? 16 : 0);
  const uint32_t hb = ub + U_PAD + (mi & 1) * U_ODD + 16 * ((lane >> 4) + (lane & 7)) - 16;
  const uint32_t kv = lds16(tb + T_KC + 16 + 2 * 512);
  const int oh = c < 2 ? 8 + 2 * c : 2 * c - 8, og = c < 3 ? 2 * c : -10;
  uint32_t bx[4] = {box2w(g - 4, 9, 2 * c), box2w(g - 3, 7, 2 * c), box2w(g - 4, 9, oh), box2w(g - 3, 7, oh)};
  uint32_t by[4] = {box2w(g - 10, 5, 2 * c - 8), box2w(g - 5, 3, 2 * c - 8), box2w(g - 10, 5, og), box2w(g - 5, 3, og)};
  uint32_t lb0 = ((unsigned)(x + 5) < 2u ? kv : 0u) | ((unsigned)(x + 4) < 2u ? kv << 16 : 0u);
  uint32_t lb1 = ((unsigned)(x - 3) < 2u ? kv : 0u) | ((unsigned)(x - 4) < 2u ? kv << 16 : 0u);
  const int q0 = g - 1, q1 = c < 3 ? g : g - 2;
  uint32_t y0a = ub + U_PAD + (q0 & 1) * U_ODD + 16 * (q0 >> 1) + 4 * c;
  uint32_t y1a = ub + U_PAD + (q1 & 1) * U_ODD + 16 * (q1 >> 1) + 4 * c;
#pragma unroll
  for (int i = 0; i < 4; i++) asm volatile("" : "+r"(bx[i]), "+r"(by[i]));
  asm volatile("" : "+r"(lb0), "+r"(lb1), "+r"(y0a), "+r"(y1a));
  mbar_wait(BAR(MB_UFULL));
  mbar_spin(BAR(MB_EMPTY + 15));
  TS(36);
  float acc[16][4];
  {
    uint32_t z09[8], z07[8], zm9[8], zm7[8];
#pragma unroll
    for (int i = 0; i < 8; i++) {
      uint32_t h[4];
      ldsm4(h, hb + 128 * i);
      float y0, y1, y2, y3, w0, w1, w2, w3;
      mma0(y0, y1, y2, y3, bx[0], bx[1], bx[2], bx[3], h[2], c < 2 ? h[3] : h[1]);
      mma0(w0, w1, w2, w3, bx[0], bx[1], bx[2], bx[3], h[1], c < 2 ? h[2] : h[0]);
      z09[i] = pack_bf(y0, y1); z07[i] = pack_bf(y2, y3);
      zm9[i] = pack_bf(w0, w1); zm7[i] = pack_bf(w2, w3);
    }
  uint32_t f3[3][4][4];
  {
    const uint32_t fa = tb + T_7 + 4 * (16 + x);
#pragma unroll
    for (int tt = 0; tt < 3; tt++)
#pragma unroll
      for (int D = 0; D < 4; D++) {
        const uint32_t a = fa + (tt == 0 ? 316 : (tt == 1 ? 320 : 0)) + 64 * D;
        f3[tt][D][0] = lds32(a); f3[tt][D][1] = lds32(a + 32); f3[tt][D][2] = lds32(a - 32); f3[tt][D][3] = lds32(a);
      }
  }
    float a[4][2][4];
#pragma unroll
    for (int kap = 0; kap < 4; kap++)
#pragma unroll
      for (int sg = 0; sg < 2; sg++)
#pragma unroll
        for (int bk = 3; bk >= kap; bk--) {
          const uint32_t(&q0_)[4] = f3[sg ? 2 : 0][bk - kap];
          const uint32_t(&q1_)[4] = f3[sg ? 2 : 1][bk - kap];
          float(&a0)[4] = a[bk][0];
          float(&a1)[4] = a[bk][1];
          if (sg == 0 && kap == 0) {
            mma0(a0[0], a0[1], a0[2], a0[3], q0_[0], q0_[1], q0_[2], q0_[3], z09[0], z09[1]);
            mma0(a1[0], a1[1], a1[2], a1[3], q1_[0], q1_[1], q1_[2], q1_[3], zm9[0], zm9[1]);
          } else {
            mma(a0[0], a0[1], a0[2], a0[3], q0_[0], q0_[1], q0_[2], q0_[3], sg ? zm7[2 * kap] : z09[2 * kap], sg ? zm7[2 * kap + 1] : z09[2 * kap + 1]);
            mma(a1[0], a1[1], a1[2], a1[3], q1_[0], q1_[1], q1_[2], q1_[3], sg ? z07[2 * kap] : zm9[2 * kap], sg ? z07[2 * kap + 1] : zm9[2 * kap + 1]);
          }
        }
    SPLIT();
#pragma unroll
    for (int i = 0; i < 8; i++) {
      uint32_t h[4];
      ldsm4(h, qa + 128 * i);
      const float ci[4] = {a[i >> 1][0][2 * (i & 1)], a[i >> 1][0][2 * (i & 1) + 1], a[i >> 1][1][2 * (i & 1)], a[i >> 1][1][2 * (i & 1) + 1]};
      mmac(acc[8 + i], h[0], h[1], h[2], h[3], lb0, lb1, ci);
    }
  }
  TS(44);
  {
    uint2 a5[10], a3[10];
    const uint32_t aa = tb + T_5 + 4 * (8 + 2 * g - 2 * c);
#pragma unroll
    for (int m = 0; m < 10; m++) { a5[m] = lds64(aa + 32 * m); a3[m] = lds64(aa + 384 + 32 * m); }
    uint32_t x5[12][2], x3[12][2];
    auto ygen = [&](int kap) {
#pragma unroll
      for (int hh = 0; hh < 2; hh++) {
        float y0, y1, y2, y3;
        mma0(y0, y1, y2, y3, by[0], by[1], by[2], by[3], lds32(y0a + 128 * kap + 64 * hh), lds32(y1a + 128 * kap + 64 * hh));
        x5[kap][hh] = pack_bf(y0, y1);
        x3[kap][hh] = pack_bf(y2, y3);
      }
    };
    ygen(11); ygen(10); ygen(9); ygen(8);
#pragma unroll
    for (int kap = 11; kap >= 0; kap--) {
      if (kap >= 4) ygen(kap - 4);
#pragma unroll
      for (int sg = 0; sg < 2; sg++)
#pragma unroll
        for (int i = 4; i >= 0; i--) {
          const int be = kap + 4 + i;
          if (be <= 15) {
            const uint2 &hi = sg ? a3[2 * i + 1] : a5[2 * i + 1], &lo = sg ? a3[2 * i] : a5[2 * i];
            const uint32_t b0 = sg ? x3[kap][0] : x5[kap][0], b1 = sg ? x3[kap][1] : x5[kap][1];
            if (be < 8 && i == 0 && sg == 0) mma0(acc[be][0], acc[be][1], acc[be][2], acc[be][3], hi.x, hi.y, lo.x, lo.y, b0, b1);
            else mma(acc[be][0], acc[be][1], acc[be][2], acc[be][3], hi.x, hi.y, lo.x, lo.y, b0, b1);
          }
        }
    }
  }
  TS(45);
  {
    const uint32_t st = tb + T_ST + lane * 8;
#pragma unroll
    for (int be = 4; be < 12; be++) sts64(st + 256 * be, pack_bf(acc[be][0], acc[be][1]), pack_bf(acc[be][2], acc[be][3]));
    SPLIT();
    uint32_t F[66], qd[8][4];
    const uint32_t fa = tb + T_D + 32 + 4 * x;
#pragma unroll
    for (int i = 0; i < 32; i++) {
      const int s = 120 - (i >> 2) - 8 * (i & 3);
      uint32_t(&q)[4] = qd[i & 7];
      ldsm4(q, qa + 16 * s);
      const int m = 16 * (i & 3) + 2 * (i >> 2);
      F[m] = lds32(fa + 32 * m); F[m + 1] = lds32(fa + 32 * m + 32);
#pragma unroll
      for (int be = 15; be >= 12; be--) {
        const int de = 8 * be - s;
        float(&a)[4] = (be >= 14 && !(i & 1)) ? acc[be - 4] : acc[be];
        if (de >= 0 && be >= 14 && i == 2 * (15 - be)) mma0(a[0], a[1], a[2], a[3], q[0], q[1], q[2], q[3], F[2 * de + 1], F[2 * de]);
        else if (de >= 0) mma(a[0], a[1], a[2], a[3], q[0], q[1], q[2], q[3], F[2 * de + 1], F[2 * de]);
      }
    }
#pragma unroll
    for (int i = 0; i < 8; i++) acc[14 + (i >> 2)][i & 3] += acc[10 + (i >> 2)][i & 3];
    F[64] = lds32(fa + 32 * 64); F[65] = lds32(fa + 32 * 65);
    uint32_t qp = qa + 128 * 11, sta = st + 256 * 10;
    uint4* yd = ydst + 7 * 32;
#pragma unroll
    for (int i = 0; i < 6; i++) ldsm4(qd[i], qp - 16 * i);
    uint2 sv = lds64(sta + 256);
    float ci[4] = {bf_lo(sv.x), bf_hi(sv.x), bf_lo(sv.y), bf_hi(sv.y)};
    float T[5][4];
#pragma unroll
    for (int i = 0; i < 16; i++) T[i >> 2][i & 3] = acc[12 + (i >> 2)][i & 3];
    nb_sync(NB_YZ, 160);
    TS(46);
#pragma unroll 1
    for (int bp = 5; bp >= 0; bp--) {
      uint32_t held[2];
#pragma unroll
      for (int o = 1; o >= 0; o--) {
#pragma unroll
        for (int k = 4; k >= 1; k--) mmac(T[k], qd[0][0], qd[0][1], qd[0][2], qd[0][3], F[16 * k + 1], F[16 * k], T[k - 1]);
        mmac(T[0], qd[0][0], qd[0][1], qd[0][2], qd[0][3], F[1], F[0], ci);
        ldsm4(qd[6], qp - 16 * 6);
        ldsm4(qd[7], qp - 16 * 7);
        sv = lds64(sta);
#pragma unroll
        for (int i = 1; i < 8; i++) {
#pragma unroll
          for (int k = 3; k >= 0; k--)
            mma(T[k][0], T[k][1], T[k][2], T[k][3], qd[i][0], qd[i][1], qd[i][2], qd[i][3], F[16 * k + 2 * i + 1], F[16 * k + 2 * i]);
          if (i < 7) ldsm4(qd[i - 1], qp - 128 - 16 * (i - 1));
          if (i == 2) {
            const uint32_t w0 = pack_bf(T[4][0], T[4][1]), w1 = pack_bf(T[4][2], T[4][3]);
            if (o) { held[0] = w0; held[1] = w1; }
            else st_x(yd, nz(w0), w1, held[0], held[1]);
          }
          if (i == 4) {
            if (2 * bp + o <= 4) sv = make_uint2(0, 0);
            ci[0] = bf_lo(sv.x); ci[1] = bf_hi(sv.x); ci[2] = bf_lo(sv.y); ci[3] = bf_hi(sv.y);
          }
        }
        qp -= 128; sta -= 256;
      }
      yd -= 32;
      if (!(bp & 1)) nb_arrive(NB_Y + 1 + (bp >> 1), 160);
    }
#pragma unroll
    for (int B = 1; B >= 0; B--)
      st_x(ydst + B * 32, nz(pack_bf(T[2 * B][0], T[2 * B][1])), pack_bf(T[2 * B][2], T[2 * B][3]),
           pack_bf(T[2 * B + 1][0], T[2 * B + 1][1]), pack_bf(T[2 * B + 1][2], T[2 * B + 1][3]));
  }
}

__device__ __forceinline__ void dual_exp(const uint32_t* w, uint32_t* e) {
  const float L = 1.44268798828125f;
  uint32_t mx = bmax2(bmax2(w[0], w[1]), bmax2(w[2], w[3]));
  uint32_t mn = bmin2(bmin2(w[0], w[1]), bmin2(w[2], w[3]));
  mx = bmax2(mx, __shfl_xor_sync(0xffffffffu, mx, 1));
  mn = bmin2(mn, __shfl_xor_sync(0xffffffffu, mn, 1));
  mx = bmax2(mx, __shfl_xor_sync(0xffffffffu, mx, 2));
  mn = bmin2(mn, __shfl_xor_sync(0xffffffffu, mn, 2));
  const float mx0 = bf_lo(mx) * -L, mx1 = bf_hi(mx) * -L, mn0 = bf_lo(mn) * L, mn1 = bf_hi(mn) * L;
#pragma unroll
  for (int i = 0; i < 2; i++) {
    const float a0 = bf_lo(w[2 * i]), a1 = bf_hi(w[2 * i]), b0 = bf_lo(w[2 * i + 1]), b1 = bf_hi(w[2 * i + 1]);
    e[2 * i] = pack_bf(ex2(fmaf(a0, L, mx0)), ex2(fmaf(b0, L, mx0)));
    e[2 * i + 1] = pack_bf(ex2(fmaf(a1, L, mx1)), ex2(fmaf(b1, L, mx1)));
    e[4 + 2 * i] = pack_bf(ex2(fmaf(a0, -L, mn0)), ex2(fmaf(b0, -L, mn0)));
    e[5 + 2 * i] = pack_bf(ex2(fmaf(a1, -L, mn1)), ex2(fmaf(b1, -L, mn1)));
  }
}
__device__ __forceinline__ void normalise(uint32_t* e, const float (&s)[4]) {
  const uint32_t r = pack_bf(rcp(s[0]), rcp(s[2]));
  const __nv_bfloat162 rr = *(const __nv_bfloat162*)&r;
#pragma unroll
  for (int i = 0; i < 4; i++) {
    const __nv_bfloat162 v = __hmul2(*(const __nv_bfloat162*)&e[i], (i & 1) ? __high2bfloat162(rr) : __low2bfloat162(rr));
    e[i] = *(const uint32_t*)&v;
  }
}
__host__ __device__ constexpr uint64_t qdesc(uint32_t addr) { return mkdesc(addr, 128, 256, 0); }

__global__ void __launch_bounds__(NTHREADS, 1)
fused_kernel(const Params P, const __grid_constant__ CUtensorMap mx, const __grid_constant__ CUtensorMap mw,
             const __grid_constant__ CUtensorMap mo, const __grid_constant__ CUtensorMap mu,
             const __grid_constant__ CUtensorMap mout, const __grid_constant__ CUtensorMap mw4) {
  constexpr uint32_t sb = SB;
  const int tid = threadIdx.x, lane = tid & 31;
  const int warp = __shfl_sync(0xffffffffu, tid >> 5, 0);
  const int b = blockIdx.x, oct = b >> 3, i8 = b & 7;
  const int rt = (((oct & 4) ? ~oct : oct) & 3) * 2 + (i8 >> 2);
  const int hp = (oct >> 2) * 4 + (i8 & 3);

  const int wg = warp >> 2, w = warp & 3;
  const int d = b * 4 + ((tid >> 5) & 3);
  const KgenRaw raw = kgen_load(P, d, tid >> 7, lane);
  const unsigned short dsk = __ldg((const unsigned short*)P.Dskip + d);
  if (tid < 384) {
    asm volatile("prefetch.tensormap [%0];" ::"l"(&mu) : "memory");
    asm volatile("prefetch.tensormap [%0];" ::"l"(&mw) : "memory");
    asm volatile("prefetch.tensormap [%0];" ::"l"(&mx) : "memory");
    asm volatile("prefetch.tensormap [%0];" ::"l"(&mw4) : "memory");
  }
  if (warp == 12) {
    if (lane == 0) {
#pragma unroll
      for (int i = 0; i < 9; i++) mbar_init(BAR(i), 1);
      asm volatile("fence.mbarrier_init.release.cluster;" ::: "memory");
    }
    __syncwarp();
    if (lane < 9) mbar_expect(BAR(0) + 8 * lane, (lane == 5 || lane == 7) ? 40960 : ((lane == 0 || lane > 5) ? 16384 : 28672));
    __syncwarp();
    e_tma3d(sb + OFF_W, &mw, BAR(MB_FULL), hp * 32, 0, 0);
    e_tma2d(sb + OFF_X + 3 * 16384, &mx, BAR(MB_FULL), 0, rt * 256);
    nb_arrive(NB_PROD, 192);
  } else if (warp == 14) {
    e_prefetch(P.x + (size_t)(rt * 256 + hp * 8) * 512, 8192);
  } else if (warp == 13) {
    if (lane == 0) {
#pragma unroll
      for (int i = 9; i < 39; i++) mbar_init(BAR(i), i < MB_EMPTY ? 1 : (i < MB_AUX ? 4 : 8));
      asm volatile("fence.mbarrier_init.release.cluster;" ::: "memory");
    }
    __syncwarp();
    if (lane < 13 && lane != 9) mbar_expect(BAR(MB_FULL + 8) + 8 * lane, lane < 8 ? 16384 : (lane == 8 ? 131072 : (lane == 10 ? 8192 : (lane == 11 ? 24576 : 32768))));
    nb_arrive(NB_PROD, 192);
  }
  const uint32_t tb = sb + OFF_T + w * T_CH;
  const uint32_t kp = wg >= 2 ? sb + OFF_STG0 + 16384 + w * 2048 : ((tb + 127) & ~127u) + wg * 2048;
  const KgenAddr kad = kgen_addr(lane, wg == 3 ? sb + OFF_X + 32768 + w * 2048 : kp);
  if (wg == 1) nb_sync(NB_PROD, 192);
  if (warp == 12) {
#pragma unroll 1
    for (int kb = 1; kb < 4; kb++) {
      if (kb == U_AT) e_tma4d(sb + OFF_STG0, &mu, BAR(MB_URAW), i8 * 64, oct * 2);
      e_tma3d(sb + OFF_W + kb * 12288, &mw, BAR(MB_FULL) + 8 * kb, hp * 32, kb * 64, 0);
      e_tma2d(sb + OFF_X + (kb < 2 ? kb + 3 : kb - 2) * 16384, &mx, BAR(MB_FULL) + 8 * kb, kb * 64, rt * 256);
    }
    e_tma4d(sb + OFF_W + 4 * 12288, &mw4, BAR(MB_FULL + 4), hp * 32, 4);
    e_tma4d(sb + OFF_W + 6 * 12288, &mw4, BAR(MB_FULL + 6), hp * 32, 6);
    if (smem_u32(smem_raw) != SB) __trap();
    if (lane == 0) TS1(54);
  }
  float k[5][4], k2048, ksc;
  kgen_unit(raw, kad, blockIdx.y, k, k2048, ksc);
  TS(40 + wg);
  if ((fu(k[0][0]) & fu(k[1][0]) & fu(k[2][0]) & fu(k[3][0]) & fu(k[4][0])) == 0xffffffffu) sts32(kp, 0);
  if (wg == 3) {
    nb_sync(0, 512);
    if (warp == 12) {
      asm volatile("fence.proxy.async.shared::cta;" ::: "memory");
      e_tma2d(sb + OFF_X + 2 * 16384, &mx, BAR(MB_FULL + 4), 256, rt * 256);
      if (X2_AT < 0) e_prefetch(P.x + (size_t)(rt * 256 + 128 + hp * 8) * 512, 8192);
    }
  } else if (wg) {
    nb_arrive(0, 512);
  }
  k2048 += __shfl_xor_sync(0xffffffffu, k2048, 16);
  k2048 += __shfl_xor_sync(0xffffffffu, k2048, 8);
  if (wg != 2) {
    uint32_t h[10];
#pragma unroll
    for (int j = 0; j < 10; j++) h[j] = hu(__floats2half2_rn(k[j >> 1][2 * (j & 1)], k[j >> 1][2 * (j & 1) + 1]));
    sts128(kp + lane * 16, h[0], h[1], h[2], h[3]);
    sts128(kp + 512 + lane * 16, h[4], h[5], h[6], h[7]);
    sts128(kp + 1024 + lane * 16, h[8], h[9], fu(k2048), fu(ksc));
  }
  if (wg == 0) { nb_arrive(NB_PREP, 512); nb_sync(0, 512); }
  else if (wg != 2) nb_arrive(NB_PREP, 512);
  else nb_sync(NB_PREP, 512);
  if (warp >= 12) {
    asm volatile("setmaxnreg.dec.sync.aligned.u32 32;");
    if (warp == 12) {
      uint32_t slot = sb + OFF_X + 3 * 16384;
#pragma unroll 1
      for (int n = 0; n < 11; n++) {
        mbar_spin(BAR(MB_EMPTY) + 8 * n);
        const int m = n + 5;
        e_tma2d(slot, &mx, BAR(MB_FULL) + 8 * m, (m & 7) * 64, rt * 256 + (m >> 3) * 128);
        slot = slot == sb + OFF_X + 4 * 16384 ? sb + OFF_X : slot + 16384;
        if (n == X2_AT) e_prefetch(P.x + (size_t)(rt * 256 + 128 + hp * 8) * 512, 8192);
        if (n == 7) {
          e_prefetch(P.wo + (size_t)b * 2048, 4096);
          asm volatile("prefetch.tensormap [%0];" ::"l"(&mo) : "memory");
          asm volatile("prefetch.tensormap [%0];" ::"l"(&mout) : "memory");
        }
      }
#pragma unroll 1
      for (int i = 0; i < 8; i++) {
        mbar_wait(BAR(MB_EMPTY + 10) + 8 * ((0x54332222u >> (4 * i)) & 7));
        const int w0 = (0x54736210u >> (4 * i)) & 7;
        e_tma3d(sb + OFF_W + w0 * 16384, &mo, BAR(MB_WO), 0, w0 * 64, (hp & 3) * 2);
      }
    } else {
      if (warp == 15) {
        const uint4 v0 = __ldg((const uint4*)P.wphi + hp * 64 + lane), v1 = __ldg((const uint4*)P.wphi + hp * 64 + 32 + lane);
        sts128(sb + OFF_PHI + (lane & 1) * 256 + (lane >> 1) * 16, v0.x, v0.y, v0.z, v0.w);
        sts128(sb + OFF_PHI + 512 + (lane & 1) * 256 + (lane >> 1) * 16, v1.x, v1.y, v1.z, v1.w);
        const uint32_t one = (((lane >> 3) ^ (lane >> 4)) & 1) ? 0u : ((lane & 1) ? 0x3F800000u : 0x3F80u);
        const int q = (lane >> 1) & 3;
        sts128(sb + OFF_EYE + lane * 16, q == 0 ? one : 0u, q == 1 ? one : 0u, q == 2 ? one : 0u, q == 3 ? one : 0u);
        sts64(sb + OFF_ONE + lane * 8, 0x3F803F80u, 0x3F803F80u);
        asm volatile("fence.proxy.async.shared::cta;" ::: "memory");
        nb_arrive(NB_KREAD, 160);
      }
      uint32_t* cnt = (uint32_t*)(P.xs + X_CNT) + (warp == 13 ? i8 : (warp == 14 ? 8 + rt : 16 + oct)) * 32;
      const unsigned target = (ld_x32(cnt) & ~15u) + 16;
      if (warp != 14) {
        if (warp == 15) mbar_wait(BAR(MB_EMPTY + ZERO_STEP));
        uint4* pz = P.xs + (warp == 13 ? X_PART + (hp * 8 + rt) * 144 : X_Y + b * 1024) + lane;
#pragma unroll 1
        for (int i = (warp == 13 ? 144 : 1024) - lane; i > 0; i -= 32, pz += 32) st_x(pz, 0, 0, 0, 0);
      }
      if (warp == 15) __syncwarp();
      else nb_sync(warp == 13 ? NB_INIT : NB_ODONE, warp == 13 ? 160 : 288);
      if (lane == 0) asm volatile("red.release.gpu.global.add.u32 [%0], %1;" ::"l"(cnt), "r"(warp == 15 ? 2 : 1) : "memory");
      if (lane == 0) TS1(warp == 13 ? 50 : (warp == 14 ? 57 : 53));
      asm volatile("fence.proxy.async.shared::cta;" ::: "memory");
      if (warp == 13) cnt += ((lane & 1 ? b >> 4 : i8 ^ (lane & 4)) - i8) * 32;
#pragma unroll 1
      for (int i = 0; i < SPIN_MAX; i++) {
        unsigned v;
        asm volatile("ld.acquire.gpu.global.u32 %0, [%1];" : "=r"(v) : "l"(cnt) : "memory");
        if (__all_sync(0xffffffffu, (int)(v - target) >= 0)) break;
      }
      if (lane == 0) TS1(warp == 13 ? 51 : (warp == 14 ? 58 : 55));
      if (warp == 15) { nb_arrive(NB_YZ, 160); return; }
      asm volatile("fence.proxy.async.global;" ::: "memory");
      if (warp == 13) {
        mbar_wait(BAR(MB_EMPTY + 11));
        e_expect(BAR(MB_UFULL), 4 * U_CH);
        e_bulk(sb + OFF_U, P.xs + X_UT + b * (U_CH / 4), 4 * U_CH, BAR(MB_UFULL));
      } else {
        const uint4* src = P.xs + X_O + (rt * 4 + (hp >> 2)) * 4096;
        e_bulk(sb + OFF_X + 32768 + 57344, src + 3584, 8192, BAR(MB_OA));
        e_bulk(sb + OFF_X + 32768, src, 32768, BAR(MB_OC));
        e_bulk(sb + OFF_STG0, src + 3200, 6144, BAR(MB_OB));
        nb_sync(NB_BDONE, 288);
        asm volatile("fence.proxy.async.shared::cta;" ::: "memory");
        e_bulk(sb + OFF_U, src + 2048, 18432, BAR(MB_OB));
      }
    }
    return;
  }

  const int t = tid & 127;
  const int g = lane >> 2, c = lane & 3;
  if (wg == 1) {
    mbar_wait(BAR(MB_URAW));
    TS(48);
    uint4* dst = P.xs + X_UT + (i8 * 64 + g) * (U_CH / 16) + (w & 1) * (U_ODD / 16) + U_PAD / 16 + oct * 8 + (w >> 1) * 4 + c;
    const int ln = ((lane >> 1) & 3) + 4 * (lane & 1);
    uint32_t r[8][4];
#pragma unroll
    for (int i = 0; i < 8; i++) ldsm4t(r[i], sb + OFF_STG0 + w * 4096 + ((lane >> 3) * 8 + ln) * 128 + ((i ^ ln) << 4));
#pragma unroll
    for (int i = 0; i < 8; i++) dst[i * (U_CH / 2)] = make_uint4(r[i][0], r[i][1], r[i][2], r[i][3]);
    nb_arrive(NB_INIT, 160);
    if (lane == 0) mbar_arrive(BAR(MB_AUX));
  }
  {
    if (wg == 2) {
      asm volatile("setmaxnreg.inc.sync.aligned.u32 160;");
#pragma unroll
      for (int j = 0; j < 5; j++) { k[j][0] *= ksc; k[j][1] *= ksc; k[j][2] *= ksc; k[j][3] *= ksc; }
#pragma unroll 1
      for (int q = 0; q < 3; q++) {
        const uint32_t src = (q == 2 ? kp : ((tb + 127) & ~127u) + q * 2048) + lane * 16;
        const uint4 v0 = lds128(src), v1 = lds128(src + 512), v2 = lds128(src + 1024);
        const uint32_t h[10] = {v0.x, v0.y, v0.z, v0.w, v1.x, v1.y, v1.z, v1.w, v2.x, v2.y};
#pragma unroll
        for (int j = 0; j < 10; j++) {
          const float2 f = __half22float2(*(const __half2*)&h[j]);
          k[j >> 1][2 * (j & 1)] = fmaf(f.x, uf(v2.w), k[j >> 1][2 * (j & 1)]);
          k[j >> 1][2 * (j & 1) + 1] = fmaf(f.y, uf(v2.w), k[j >> 1][2 * (j & 1) + 1]);
        }
        k2048 += uf(v2.z);
      }
#pragma unroll
      for (int o2 = 4; o2; o2 >>= 1) k2048 += __shfl_xor_sync(0xffffffffu, k2048, o2);
      if (lane == 0) k[0][0] += bf_lo(dsk);
      __syncwarp();
      if (lane == 0) mbar_arrive(BAR(MB_AUX));
      TS(34);
      build_tables(tb, lane, k, k2048);
      TS(35);
      uint4* const g_y = P.xs + X_Y;
      conv_channel(sb + OFF_U + w * U_CH, tb, lane, g_y + (size_t)d * 256 + lane);
      nb_arrive(NB_BDONE, 288);
      nb_arrive(NB_Y, 160);
      TS(37);
      if (w == 0) TSDUMP(32);
      return;
    }
    if (wg == 1) {
      mbar_wait(BAR(MB_EMPTY + 4));
      mbar_spin(BAR(MB_EMPTY + 6));
    }
    TS(wg * 16 + 1);
  }

  float acc[2][48];
  {
    uint32_t fb = BAR(MB_FULL) + 64 * wg;
    uint32_t da = (uint32_t)mkdesc(sb + OFF_X, 16, 0, 0) + (wg ? 1024 : 3072), db = (uint32_t)mkdesc(sb + OFF_W, 4096, 0, 0);
    constexpr uint64_t ha = mkdesc(0, 0, 1024, 1), hb = mkdesc(0, 0, 512, 2);
    mbar_spin(fb);
    TS(wg * 16 + 2);
#pragma unroll 1
    for (int kb = 0; kb < 8; kb++) {
      WG_FENCE();
#pragma unroll
      for (int k = 0; k < 4; k++) {
        wgmma_ss_n96(acc[0], ha | (da + 2 * k), hb | (db + 64 * k), k ? 1 : kb);
        wgmma_ss_n96(acc[1], ha | (da + 2 * k + 512), hb | (db + 64 * k), k ? 1 : kb);
      }
      WG_COMMIT();
      if (kb < 7) mbar_spin(fb + 8);
      WG_WAIT(1);
      if (kb > 0) e_arrive(fb + 8 * (MB_EMPTY - MB_FULL - 1));
      fb += 8; db += 768;
      da = da == (uint32_t)mkdesc(sb + OFF_X + 65536, 16, 0, 0) ? da - 4096 : da + 1024;
    }
    if (wg == 0) nb_sync(NB_KREAD, 160);
    asm volatile("setmaxnreg.inc.sync.aligned.u32 160;");
    WG_WAIT(0);
    e_arrive(fb + 8 * (MB_EMPTY - MB_FULL - 1));
    SPLIT();
  }
  TS(wg * 16 + 3);

  constexpr uint32_t stg0 = sb + OFF_STG0, stg1 = sb + OFF_X + 32768;
  uint4* const g_part = P.xs + X_PART;
  uint4* const g_o = P.xs + X_O;
  constexpr uint32_t kvs = stg0;
  auto pack8 = [](const float* a) { return make_uint4(pack_bf(a[0], a[1]), pack_bf(a[2], a[3]), pack_bf(a[4], a[5]), pack_bf(a[6], a[7])); };
  auto feat = [&](const uint4 (&af)[4], float (&p)[4][8]) {
    WG_FENCE();
#pragma unroll
    for (int u = 0; u < 4; u++) wgmma_rs_n16(p[u], af[u], qdesc(sb + OFF_PHI + (u & 1) * 512), 0);
    WG_COMMIT();
  };
  auto packp = [](const float (&p)[4][8], uint32_t (&pw)[16]) {
#pragma unroll
    for (int i = 0; i < 16; i++) pw[i] = pack_bf(p[i >> 2][(i & 1) + 2 * (i & 2)], p[i >> 2][(i & 1) + 2 * (i & 2) + 2]);
  };
  auto contract = [&](float (&kc)[20], uint32_t stg, int acc_in) {
    WG_FENCE();
#pragma unroll
    for (int s = 0; s < 8; s++) wgmma_ss_n40(kc, qdesc(stg + s * SLAB), qdesc(stg + s * SLAB + 2048), s ? 1 : acc_in);
    WG_COMMIT();
    WG_WAIT(0);
  };
  uint32_t eq[32];
  {
    uint4 af[4], aq[4], vp[4];
    float p[4][8];
#pragma unroll
    for (int u = 0; u < 4; u++) af[u] = pack8(acc[u >> 1] + 16 + 8 * (u & 1));
    feat(af, p);
#pragma unroll
    for (int u = 0; u < 4; u++) { aq[u] = pack8(acc[u >> 1] + 8 * (u & 1)); vp[u] = pack8(acc[u >> 1] + 32 + 8 * (u & 1)); }
    WG_WAIT(0);
    uint32_t pw[16], ek[32];
    packp(p, pw);
#pragma unroll
    for (int u = 0; u < 4; u++) dual_exp(pw + 4 * u, ek + 8 * u);
    TS(wg * 16 + 12);
    SPLIT();
    float rs[8][4];
    WG_FENCE();
#pragma unroll
    for (int i = 0; i < 8; i++) wgmma_rs_n8(rs[i], make_uint4(ek[4 * i], ek[4 * i + 1], ek[4 * i + 2], ek[4 * i + 3]), qdesc(sb + OFF_ONE), 0);
    WG_COMMIT();
    feat(aq, p);
    WG_WAIT(1);
#pragma unroll
    for (int i = 0; i < 8; i++) normalise(ek + 4 * i, rs[i]);
    WG_WAIT(0);
#pragma unroll 1
    for (int ph = 0; ph < 2; ph++) {
      if (ph == wg) {
        packp(p, pw);
#pragma unroll
        for (int u = 0; u < 4; u++) dual_exp(pw + 4 * u, eq + 8 * u);
        TS(wg * 16 + 4);
      } else {
        mbar_spin(wg ? BAR(MB_EMPTY + 15) : BAR(MB_AUX));
        uint32_t sl = (wg ? stg1 : stg0) + w * SLAB + lane * 16;
        asm volatile("" : "+r"(sl));
#pragma unroll
        for (int i = 0; i < 8; i++) stsm4(sl + (i >> 2) * 4 * SLAB + (i & 3) * 512, ek[4 * i], ek[4 * i + 1], ek[4 * i + 2], ek[4 * i + 3]);
#pragma unroll
        for (int i = 0; i < 4; i++) stsm4(sl + (i >> 1) * 4 * SLAB + 2048 + (i & 1) * 512, vp[i].x, vp[i].y, vp[i].z, vp[i].w);
        sts128(sl + (lane >> 4) * (4 * SLAB - 256) + 3072, 0x3F803F80u, 0x3F803F80u, 0x3F803F80u, 0x3F803F80u);
        asm volatile("fence.proxy.async.shared::cta;" ::: "memory");
        if (wg) {
          nb_arrive(NB_ST0, 256);
        }
        TS(wg * 16 + 13);
      }
    }
  }
  if (wg == 0) {
    {
      float kc[20];
      uint4* pp = g_part + (size_t)(hp * 8 + rt) * 144 + t;
      uint32_t* pz = (uint32_t*)(pp - t + 128) + w * 16 + c * 8 + g;
      asm volatile("" : "+l"(pp), "+l"(pz));
      nb_sync(NB_WG0, 128);
      contract(kc, stg0, 0);
      mbar_wait(BAR(MB_UFULL));
      TS(15);
      nb_sync(NB_ST0, 256);
      contract(kc, stg1, 1);
      TS(6);
      float kv[8];
#pragma unroll
      for (int i = 0; i < 8; i++) kv[i] = w & 2 ? kc[8 + i] : kc[i];
      st_x(pp, nz(pack_bf(kv[0], kv[1])), pack_bf(kv[2], kv[3]), pack_bf(kv[4], kv[5]), pack_bf(kv[6], kv[7]));
      if (c < 2) st_x32(pz, nz(fu(c ? kc[18] : kc[16])));
      TS(5);
    }
    const uint4* ps = g_part + (size_t)hp * 8 * 144 + t;
    const uint32_t* zs = (const uint32_t*)(g_part + (size_t)(hp * 8 + (lane >> 4) * 4) * 144 + 128) + w * 16 + (lane & 15);
    uint4 v[8];
    uint32_t zv[4];
#pragma unroll 1
    for (int it = 0; it < SPIN_MAX; it++) {
#pragma unroll
      for (int i = 0; i < 8; i++) v[i] = ld_x(ps + i * 144);
#pragma unroll
      for (int i = 0; i < 4; i++) zv[i] = ld_x32(zs + i * 576);
      uint32_t m = min(min(zv[0], zv[1]), min(zv[2], zv[3]));
#pragma unroll
      for (int i = 0; i < 8; i++) m = min(m, v[i].x);
      if (__all_sync(0xffffffffu, m != 0)) break;
    }
    float s[8];
    WG_FENCE();
#pragma unroll
    for (int r = 0; r < 8; r++) wgmma_rs_n16(s, v[r], qdesc(sb + OFF_EYE), r);
    WG_COMMIT();
    float zsum = (uf(zv[0]) + uf(zv[1])) + (uf(zv[2]) + uf(zv[3]));
    zsum += __shfl_xor_sync(0xffffffffu, zsum, 16);
    const uint32_t z1 = pack_bf(zsum, 1.f);
    if (lane < 16) sts128(kvs + w * 768 + 512 + lane * 16, z1, z1, z1, z1);
    WG_WAIT(0);
    stsm4(kvs + w * 768 + lane * 16, pack_bf(s[0], s[1]), pack_bf(s[2], s[3]), pack_bf(s[4], s[5]), pack_bf(s[6], s[7]));
    asm volatile("fence.proxy.async.shared::cta;" ::: "memory");
    TS(0);
  }
  nb_sync(NB_KV, 256);
  {
    float n[8][12];
    WG_FENCE();
#pragma unroll
    for (int i = 0; i < 8; i++) wgmma_rs_n24(n[i], make_uint4(eq[4 * i], eq[4 * i + 1], eq[4 * i + 2], eq[4 * i + 3]), qdesc(kvs + (i & 3) * 768), 0);
    WG_COMMIT();
    uint32_t* od = (uint32_t*)(g_o + (size_t)((rt * 4 + wg * 2) * 32 + hp * 2) * 128) + w * 64 + lane;
    WG_WAIT(0);
#pragma unroll
    for (int u = 0; u < 4; u++) {
      float(&np)[12] = n[2 * u];
      const float(&nm)[12] = n[2 * u + 1];
      const float q0 = np[9] * rcp(nm[9]), q1 = np[11] * rcp(nm[11]);
      const float r0 = rcp(fmaf(nm[8], q0, fmaf(np[9], 1e-6f, np[8]))), r1 = rcp(fmaf(nm[10], q1, fmaf(np[11], 1e-6f, np[10])));
#pragma unroll
      for (int i = 0; i < 8; i++) np[i] = fmaf(nm[i], (i & 2) ? q1 : q0, np[i]);
      uint32_t* o = od + (u >> 1) * 16384 + (u & 1) * 512;
      o[0] = pack_bf(np[0] * r0, np[1] * r0);
      o[32] = pack_bf(np[2] * r1, np[3] * r1);
      o[256] = pack_bf(np[4] * r0, np[5] * r0);
      o[288] = pack_bf(np[6] * r1, np[7] * r1);
      if (u == 1) SPLIT();
    }
  }
  TS(wg * 16 + 7);
  nb_arrive(NB_ODONE, 288);
  if (wg) {
    const uint4* src = P.xs + X_Y + (oct * 32 + c * 8) * 256 + (2 * w + (g >> 2)) * 32 + i8 * 4 + (g & 3);
    __nv_bfloat16* dst = P.out + (size_t)((2 * w + (g >> 2)) * 256 + i8 * 16 + (g & 3) * 2) * 1024 + 512 + oct * 32 + c * 8;
    nb_sync(NB_Y + w, 160);
    uint4 v[8];
#pragma unroll 1
    for (int it = 0; it < SPIN_MAX; it++) {
      uint32_t m = 0xffffffffu;
#pragma unroll
      for (int i = 0; i < 8; i++) v[i] = ld_x(src + i * 256);
#pragma unroll
      for (int i = 0; i < 8; i++) m = min(m, v[i].x);
      if (__all_sync(0xffffffffu, m != 0)) break;
    }
#pragma unroll
    for (int i = 0; i < 8; i++) *(uint4*)(dst + (size_t)((i >> 2) * 128 + ((i >> 1) & 1) * 8 + (i & 1)) * 1024) = tr_row(v, i);
    TS(31);
    GT(63);
    if (w == 0) TSDUMP(16);
    return;
  }
  mbar_wait(BAR(MB_WO));
  nb_sync(NB_BDONE, 288);
  TS(8);
  mbar_spin(BAR(MB_OA));
  TS(9);
  float oc[64];
  {
    constexpr uint64_t ha = mkdesc(0, 0, 128, 0), hb = mkdesc(0, 0, 1024, 1);
    constexpr uint32_t da0 = (uint32_t)mkdesc(stg1, 1024, 0, 0), db0 = (uint32_t)mkdesc(sb + OFF_W, 8192, 0, 0);
#pragma unroll 1
    for (int j = 0; j < 8; j++) {
      const int kb = (j + 7) & 7;
      if ((j & 3) == 1) mbar_spin(j == 1 ? BAR(MB_OC) : BAR(MB_OB));
      WG_FENCE();
#pragma unroll
      for (int k = 0; k < 4; k++) wgmma_ss_n128(oc, ha | (da0 + 512 * kb + 128 * k), hb | (db0 + 1024 * kb + 128 * k), k ? 1 : j);
      WG_COMMIT();
    }
    WG_WAIT(0);
  }
  TS(10);
  const uint32_t ot = ((sb + OFF_T + 1023) & ~1023u) + w * 4096;
#pragma unroll
  for (int hf = 0; hf < 2; hf++) {
#pragma unroll
    for (int i = 8 * hf; i < 8 * hf + 8; i += 2)
      stsm4(ot + hf * 2048 + (lane & 15) * 128 + (((i + (lane >> 4)) ^ lane) & 7) * 16, pack_bf(oc[4 * i], oc[4 * i + 1]),
            pack_bf(oc[4 * i + 2], oc[4 * i + 3]), pack_bf(oc[4 * i + 4], oc[4 * i + 5]), pack_bf(oc[4 * i + 6], oc[4 * i + 7]));
    asm volatile("fence.proxy.async.shared::cta;" ::: "memory");
    __syncwarp();
    e_store2d(&mout, ot + hf * 2048, (hp & 3) * 128 + hf * 64, (rt * 4 + (hp >> 2)) * 64 + w * 16);
  }
  asm volatile(ELECT "cp.async.bulk.commit_group;\n@p cp.async.bulk.wait_group.read 0;\n}\n" ::: "memory");
  TS(wg * 16 + 11);
  GT(61 + wg);
  if (w == 0) TSDUMP(0);
  if (w == 1) TSDUMP(48);
}

typedef CUresult (*EncodeFn)(CUtensorMap*, CUtensorMapDataType, cuuint32_t, void*, const cuuint64_t*, const cuuint64_t*,
                             const cuuint32_t*, const cuuint32_t*, CUtensorMapInterleave, CUtensorMapSwizzle,
                             CUtensorMapL2promotion, CUtensorMapFloatOOBfill);

}

extern "C" void kernel_launch(void* const* d_in, const int* in_sizes, int n_in, void* d_out, int out_size) {
  (void)in_sizes; (void)n_in; (void)out_size;
  void* fn = nullptr;
  cudaDriverEntryPointQueryResult qr;
  cudaGetDriverEntryPoint("cuTensorMapEncodeTiled", &fn, cudaEnableDefault, &qr);
  EncodeFn enc = (EncodeFn)fn;
  CUtensorMap mx, mw, mo, mu, mout, mw4;
  const cuuint32_t es[5] = {1, 1, 1, 1, 1};
  {
    cuuint64_t dims[2] = {512, 2048}, st[1] = {1024};
    cuuint32_t box[2] = {64, 128};
    enc(&mx, CU_TENSOR_MAP_DATA_TYPE_BFLOAT16, 2, d_in[0], dims, st, box, es, CU_TENSOR_MAP_INTERLEAVE_NONE,
        CU_TENSOR_MAP_SWIZZLE_128B, CU_TENSOR_MAP_L2_PROMOTION_L2_128B, CU_TENSOR_MAP_FLOAT_OOB_FILL_NONE);
  }
  {
    cuuint64_t dims[3] = {512, 512, 3}, st[2] = {3072, 1024};
    cuuint32_t box[3] = {32, 64, 3};
    enc(&mw, CU_TENSOR_MAP_DATA_TYPE_BFLOAT16, 3, d_in[1], dims, st, box, es, CU_TENSOR_MAP_INTERLEAVE_NONE,
        CU_TENSOR_MAP_SWIZZLE_64B, CU_TENSOR_MAP_L2_PROMOTION_L2_128B, CU_TENSOR_MAP_FLOAT_OOB_FILL_NONE);
  }
  {
    cuuint64_t dims[3] = {64, 512, 8}, st[2] = {1024, 128};
    cuuint32_t box[3] = {64, 64, 2};
    enc(&mo, CU_TENSOR_MAP_DATA_TYPE_BFLOAT16, 3, d_in[3], dims, st, box, es, CU_TENSOR_MAP_INTERLEAVE_NONE,
        CU_TENSOR_MAP_SWIZZLE_128B, CU_TENSOR_MAP_L2_PROMOTION_L2_128B, CU_TENSOR_MAP_FLOAT_OOB_FILL_NONE);
  }
  {
    cuuint64_t dims[4] = {512, 4, 16, 32}, st[3] = {16384, 1024, 65536};
    cuuint32_t box[4] = {64, 4, 16, 2};
    enc(&mu, CU_TENSOR_MAP_DATA_TYPE_BFLOAT16, 4, d_in[4], dims, st, box, es, CU_TENSOR_MAP_INTERLEAVE_NONE,
        CU_TENSOR_MAP_SWIZZLE_128B, CU_TENSOR_MAP_L2_PROMOTION_L2_128B, CU_TENSOR_MAP_FLOAT_OOB_FILL_NONE);
  }
  {
    cuuint64_t dims[2] = {1024, 2048}, st[1] = {2048};
    cuuint32_t box[2] = {64, 16};
    enc(&mout, CU_TENSOR_MAP_DATA_TYPE_BFLOAT16, 2, d_out, dims, st, box, es, CU_TENSOR_MAP_INTERLEAVE_NONE,
        CU_TENSOR_MAP_SWIZZLE_128B, CU_TENSOR_MAP_L2_PROMOTION_NONE, CU_TENSOR_MAP_FLOAT_OOB_FILL_NONE);
  }
  {
    cuuint64_t dims[4] = {512, 64, 3, 8}, st[3] = {3072, 1024, 64 * 3072};
    cuuint32_t box[4] = {32, 64, 3, 2};
    enc(&mw4, CU_TENSOR_MAP_DATA_TYPE_BFLOAT16, 4, d_in[1], dims, st, box, es, CU_TENSOR_MAP_INTERLEAVE_NONE,
        CU_TENSOR_MAP_SWIZZLE_64B, CU_TENSOR_MAP_L2_PROMOTION_L2_128B, CU_TENSOR_MAP_FLOAT_OOB_FILL_NONE);
  }
  Params P;
  P.x = (const __nv_bfloat16*)d_in[0];
  P.wphi = (const __nv_bfloat16*)d_in[2];
  P.wo = (const __nv_bfloat16*)d_in[3];
  P.logA = (const __nv_bfloat16*)d_in[5];
  P.Aim = (const __nv_bfloat16*)d_in[6];
  P.Cre = (const __nv_bfloat16*)d_in[7];
  P.Cim = (const __nv_bfloat16*)d_in[8];
  P.logdt = (const __nv_bfloat16*)d_in[9];
  P.Dskip = (const __nv_bfloat16*)d_in[10];
  P.out = (__nv_bfloat16*)d_out;
  cudaGetSymbolAddress((void**)&P.xs, g_x);
  P.ts = nullptr;
  cudaFuncSetAttribute(fused_kernel, cudaFuncAttributeMaxDynamicSharedMemorySize, SMEM_BYTES);
  fused_kernel<<<NCTA, NTHREADS, SMEM_BYTES>>>(P, mx, mw, mo, mu, mout, mw4);
}
```

```cpp
#include <cuda_runtime.h>
#include <cuda_bf16.h>
#include <cuda_fp16.h>
#include <cuda.h>
#include <stdint.h>

#define DBG_TS 0

namespace {

constexpr int NTHREADS = 512;
constexpr int NCTA = 128;
constexpr int OFF_W = 0;
constexpr int OFF_X = 98304;
constexpr int OFF_U = OFF_X + 65536;
constexpr int U_CH = 4416, U_ODD = 2240, U_PAD = 128;
constexpr int OFF_STG0 = OFF_U + 18432;
constexpr int SLAB = 3328;
constexpr int OFF_T = OFF_STG0 + 8 * SLAB;
constexpr int T_CH = 5216;
constexpr int T_D = 0;
constexpr int T_5 = 2144;
constexpr int T_3 = T_5 + 384;
constexpr int T_7 = T_5 + 1024;
constexpr int T_9 = T_7 + 320;
constexpr int T_KC = T_9 + 320;
constexpr int T_ST = T_5 - 1024;
constexpr int OFF_PHI = OFF_T + 4 * T_CH;
constexpr int OFF_EYE = OFF_PHI + 1024, OFF_ONE = OFF_EYE + 512;
constexpr int OFF_BAR = OFF_ONE + 256;
constexpr int SMEM_BYTES = OFF_BAR + 512 + 256 * DBG_TS;
constexpr uint32_t SB = 1024;
static_assert(T_KC + 2 * 656 <= T_CH, "table size");
static_assert(SMEM_BYTES <= 232448, "smem");
constexpr int MB_URAW = 0, MB_FULL = 1  , MB_WO = 17, MB_UFULL = 18, MB_OA = 19, MB_OB = 20, MB_OC = 21,
              MB_EMPTY = 22  , MB_AUX = 38;
__host__ __device__ constexpr uint32_t BAR(int i) { return SB + OFF_BAR + 8 * i; }
constexpr int NB_WG0 = 1, NB_ODONE = 2, NB_ST0 = 3  , NB_KV = 5, NB_YZ = 6, NB_INIT = 7, NB_PREP = 8, NB_PROD = 9, NB_KREAD = 10, NB_BDONE = 11, NB_GATE = 12,
              NB_Y = 7  ;
#define X2_AT -1
#define GATE_B 0
#define U_AT 2
#define ZERO_STEP 12
constexpr int SPIN_MAX = 1 << 16;

constexpr int X_CNT = 0;
constexpr int X_PART = 256;
constexpr int X_O = X_PART + 16 * 8 * 144;
constexpr int X_Y = X_O + 32 * 32 * 128;
constexpr int X_UT = X_Y + 512 * 8 * 32;
constexpr int X_SIZE = X_UT + 512 * (U_CH / 16);
__device__ __align__(128) uint4 g_x[X_SIZE];
extern __shared__ uint8_t smem_raw[];
#define TS(i) do {} while (0)
#define TS1(i) do {} while (0)
#define GT(i) do {} while (0)
#define TSDUMP(base) do {} while (0)

__device__ __forceinline__ uint32_t smem_u32(const void* p) { return (uint32_t)__cvta_generic_to_shared(p); }
__device__ __forceinline__ void mbar_arrive(uint32_t b) {
  asm volatile("mbarrier.arrive.shared::cta.b64 _, [%0];" ::"r"(b) : "memory");
}
__device__ __forceinline__ void mbar_wait(uint32_t b) {
  uint32_t done = 0;
#pragma unroll 1
  for (int i = 0; i < SPIN_MAX && !done; i++) {
    asm volatile("{\n.reg .pred p;\nmbarrier.try_wait.parity.shared::cta.b64 p, [%1], 0, 4000;\nselp.u32 %0, 1, 0, p;\n}\n"
                 : "=r"(done) : "r"(b) : "memory");
  }
}
__device__ __forceinline__ void mbar_spin(uint32_t b) {
  uint32_t done = 0;
#pragma unroll 1
  for (int i = 0; i < (SPIN_MAX << 4) && !done; i++) {
    asm volatile("{\n.reg .pred p;\nmbarrier.try_wait.parity.shared::cta.b64 p, [%1], 0;\nselp.u32 %0, 1, 0, p;\n}\n"
                 : "=r"(done) : "r"(b) : "memory");
  }
}
__device__ __forceinline__ void mbar_init(uint32_t b, int n) {
  asm volatile("mbarrier.init.shared::cta.b64 [%0], %1;" ::"r"(b), "r"(n) : "memory");
}
__device__ __forceinline__ void mbar_expect(uint32_t b, int bytes) {
  asm volatile("mbarrier.arrive.expect_tx.shared::cta.b64 _, [%0], %1;" ::"r"(b), "r"(bytes) : "memory");
}
__device__ __forceinline__ void nb_sync(int id, int n) { asm volatile("bar.sync %0, %1;" ::"r"(id), "r"(n) : "memory"); }
__device__ __forceinline__ void nb_arrive(int id, int n) { asm volatile("bar.arrive %0, %1;" ::"r"(id), "r"(n) : "memory"); }
#define ELECT "{\n.reg .pred p;\nelect.sync _|p, 0xffffffff;\n@p "
__device__ __forceinline__ void e_arrive(uint32_t b) {
  asm volatile(ELECT "mbarrier.arrive.shared::cta.b64 _, [%0];\n}\n" ::"r"(b) : "memory");
}
__device__ __forceinline__ void e_expect(uint32_t b, int bytes) {
  asm volatile(ELECT "mbarrier.arrive.expect_tx.shared::cta.b64 _, [%0], %1;\n}\n" ::"r"(b), "r"(bytes) : "memory");
}
__device__ __forceinline__ void e_tma2d(uint32_t dst, const CUtensorMap* m, uint32_t bar, int c0, int c1) {
  asm volatile(ELECT "cp.async.bulk.tensor.2d.shared::cluster.global.mbarrier::complete_tx::bytes [%0], [%1, {%3,%4}], [%2];\n}\n"
               ::"r"(dst), "l"(m), "r"(bar), "r"(c0), "r"(c1) : "memory");
}
__device__ __forceinline__ void e_tma3d(uint32_t dst, const CUtensorMap* m, uint32_t bar, int c0, int c1, int c2) {
  asm volatile(ELECT "cp.async.bulk.tensor.3d.shared::cluster.global.mbarrier::complete_tx::bytes [%0], [%1, {%3,%4,%5}], [%2];\n}\n"
               ::"r"(dst), "l"(m), "r"(bar), "r"(c0), "r"(c1), "r"(c2) : "memory");
}
__device__ __forceinline__ void e_tma4d(uint32_t dst, const CUtensorMap* m, uint32_t bar, int c0, int c3) {
  asm volatile(ELECT "cp.async.bulk.tensor.4d.shared::cluster.global.mbarrier::complete_tx::bytes [%0], [%1, {%3,%5,%5,%4}], [%2];\n}\n"
               ::"r"(dst), "l"(m), "r"(bar), "r"(c0), "r"(c3), "r"(0) : "memory");
}
__device__ __forceinline__ void e_bulk(uint32_t dst, const void* src, int bytes, uint32_t bar) {
  asm volatile(ELECT "cp.async.bulk.shared::cluster.global.mbarrier::complete_tx::bytes [%0], [%1], %2, [%3];\n}\n"
               ::"r"(dst), "l"(src), "r"(bytes), "r"(bar) : "memory");
}
__device__ __forceinline__ void e_prefetch(const void* p, int bytes) {
  asm volatile(ELECT "cp.async.bulk.prefetch.L2.global [%0], %1;\n}\n" ::"l"(p), "r"(bytes) : "memory");
}
__device__ __forceinline__ void e_store2d(const CUtensorMap* m, uint32_t src, int c0, int c1) {
  asm volatile(ELECT "cp.async.bulk.tensor.2d.global.shared::cta.bulk_group [%0, {%2,%3}], [%1];\n}\n"
               ::"l"(m), "r"(src), "r"(c0), "r"(c1) : "memory");
}
__host__ __device__ constexpr uint64_t mkdesc(uint32_t addr, uint32_t lbo, uint32_t sbo, int swz) {
  return (uint64_t)((addr & 0x3FFFF) >> 4) | ((uint64_t)(lbo >> 4) << 16) | ((uint64_t)(sbo >> 4) << 32) |
         ((uint64_t)swz << 62);
}
#define SPLIT() asm volatile("{\n.reg .pred p;\nsetp.eq.u32 p, %0, %1;\n@p exit;\n}\n" ::"r"(blockIdx.y), "n"(__LINE__) : "memory")
#define WG_FENCE() asm volatile("wgmma.fence.sync.aligned;" ::: "memory")
#define WG_COMMIT() asm volatile("wgmma.commit_group.sync.aligned;" ::: "memory")
#define WG_WAIT(n) asm volatile("wgmma.wait_group.sync.aligned " #n ";" ::: "memory")

__device__ __forceinline__ void mma(float& d0, float& d1, float& d2, float& d3, uint32_t a0, uint32_t a1, uint32_t a2,
                                    uint32_t a3, uint32_t b0, uint32_t b1) {
  asm volatile("mma.sync.aligned.m16n8k16.row.col.f32.bf16.bf16.f32 {%0,%1,%2,%3},{%4,%5,%6,%7},{%8,%9},{%0,%1,%2,%3};"
               : "+f"(d0), "+f"(d1), "+f"(d2), "+f"(d3)
               : "r"(a0), "r"(a1), "r"(a2), "r"(a3), "r"(b0), "r"(b1));
}
__device__ __forceinline__ void mmac(float (&d)[4], uint32_t a0, uint32_t a1, uint32_t a2, uint32_t a3, uint32_t b0,
                                     uint32_t b1, const float (&c)[4]) {
  asm volatile("mma.sync.aligned.m16n8k16.row.col.f32.bf16.bf16.f32 {%0,%1,%2,%3},{%4,%5,%6,%7},{%8,%9},{%10,%11,%12,%13};"
               : "=f"(d[0]), "=f"(d[1]), "=f"(d[2]), "=f"(d[3])
               : "r"(a0), "r"(a1), "r"(a2), "r"(a3), "r"(b0), "r"(b1), "f"(c[0]), "f"(c[1]), "f"(c[2]), "f"(c[3]));
}
__device__ __forceinline__ void mma_p(int p, float (&d)[4], uint32_t a0, uint32_t a1, uint32_t a2, uint32_t a3, uint32_t b0, uint32_t b1) {
  asm volatile("{\n.reg .pred q;\nsetp.ne.b32 q, %10, 0;\n"
               "@q mma.sync.aligned.m16n8k16.row.col.f32.bf16.bf16.f32 {%0,%1,%2,%3},{%4,%5,%6,%7},{%8,%9},{%0,%1,%2,%3};\n}\n"
               : "+f"(d[0]), "+f"(d[1]), "+f"(d[2]), "+f"(d[3])
               : "r"(a0), "r"(a1), "r"(a2), "r"(a3), "r"(b0), "r"(b1), "r"(p));
}
__device__ __forceinline__ void mmac_p(int p, float (&d)[4], uint32_t a0, uint32_t a1, uint32_t a2, uint32_t a3, uint32_t b0,
                                       uint32_t b1, const float (&c)[4]) {
  asm volatile("{\n.reg .pred q;\nsetp.ne.b32 q, %14, 0;\n"
               "@q mma.sync.aligned.m16n8k16.row.col.f32.bf16.bf16.f32 {%0,%1,%2,%3},{%4,%5,%6,%7},{%8,%9},{%10,%11,%12,%13};\n}\n"
               : "+f"(d[0]), "+f"(d[1]), "+f"(d[2]), "+f"(d[3])
               : "r"(a0), "r"(a1), "r"(a2), "r"(a3), "r"(b0), "r"(b1), "f"(c[0]), "f"(c[1]), "f"(c[2]), "f"(c[3]), "r"(p));
}
__device__ __forceinline__ void mma_h(float (&d)[4], const uint32_t (&a)[4], uint32_t b0, uint32_t b1) {
  asm volatile("mma.sync.aligned.m16n8k16.row.col.f32.f16.f16.f32 {%0,%1,%2,%3},{%4,%5,%6,%7},{%8,%9},{%0,%1,%2,%3};"
               : "+f"(d[0]), "+f"(d[1]), "+f"(d[2]), "+f"(d[3]) : "r"(a[0]), "r"(a[1]), "r"(a[2]), "r"(a[3]), "r"(b0), "r"(b1));
}
__device__ __forceinline__ void mma0(float& d0, float& d1, float& d2, float& d3, uint32_t a0, uint32_t a1, uint32_t a2,
                                     uint32_t a3, uint32_t b0, uint32_t b1) {
  asm volatile("mma.sync.aligned.m16n8k16.row.col.f32.bf16.bf16.f32 {%0,%1,%2,%3},{%4,%5,%6,%7},{%8,%9},{%10,%10,%10,%10};"
               : "=f"(d0), "=f"(d1), "=f"(d2), "=f"(d3)
               : "r"(a0), "r"(a1), "r"(a2), "r"(a3), "r"(b0), "r"(b1), "f"(0.f));
}
__device__ __forceinline__ uint32_t pack_bf(float lo, float hi) {
  uint32_t r;
  asm("cvt.rn.bf16x2.f32 %0, %1, %2;" : "=r"(r) : "f"(hi), "f"(lo));
  return r;
}
__device__ __forceinline__ float bf_lo(uint32_t w) { return __uint_as_float(w << 16); }
__device__ __forceinline__ float bf_hi(uint32_t w) { return __uint_as_float(w & 0xffff0000u); }
__device__ __forceinline__ float bf_round(float x) { return __bfloat162float(__float2bfloat16_rn(x)); }
__device__ __forceinline__ uint32_t bmax2(uint32_t a, uint32_t b) {
  uint32_t r; asm("max.bf16x2 %0, %1, %2;" : "=r"(r) : "r"(a), "r"(b)); return r;
}
__device__ __forceinline__ uint32_t bmin2(uint32_t a, uint32_t b) {
  uint32_t r; asm("min.bf16x2 %0, %1, %2;" : "=r"(r) : "r"(a), "r"(b)); return r;
}
__device__ __forceinline__ float ex2(float x) { float r; asm("ex2.approx.ftz.f32 %0, %1;" : "=f"(r) : "f"(x)); return r; }
__device__ __forceinline__ float rcp(float x) { float r; asm("rcp.approx.ftz.f32 %0, %1;" : "=f"(r) : "f"(x)); return r; }
__device__ __forceinline__ void ldsm4(uint32_t (&r)[4], uint32_t a) {
  asm volatile("ldmatrix.sync.aligned.m8n8.x4.shared.b16 {%0,%1,%2,%3}, [%4];"
               : "=r"(r[0]), "=r"(r[1]), "=r"(r[2]), "=r"(r[3]) : "r"(a) : "memory");
}
__device__ __forceinline__ void ldsm4t(uint32_t (&r)[4], uint32_t a) {
  asm volatile("ldmatrix.sync.aligned.m8n8.x4.trans.shared.b16 {%0,%1,%2,%3}, [%4];"
               : "=r"(r[0]), "=r"(r[1]), "=r"(r[2]), "=r"(r[3]) : "r"(a) : "memory");
}
__device__ __forceinline__ void stsm4(uint32_t a, uint32_t r0, uint32_t r1, uint32_t r2, uint32_t r3) {
  asm volatile("stmatrix.sync.aligned.m8n8.x4.shared.b16 [%0], {%1,%2,%3,%4};"
               ::"r"(a), "r"(r0), "r"(r1), "r"(r2), "r"(r3) : "memory");
}
__device__ __forceinline__ uint32_t lds32(uint32_t a) {
  uint32_t r; asm volatile("ld.shared.u32 %0, [%1];" : "=r"(r) : "r"(a) : "memory"); return r;
}
__device__ __forceinline__ uint32_t lds16(uint32_t a) {
  uint32_t r; asm volatile("{\n.reg .u16 h;\nld.shared.u16 h, [%1];\ncvt.u32.u16 %0, h;\n}\n" : "=r"(r) : "r"(a) : "memory"); return r;
}
__device__ __forceinline__ uint2 lds64(uint32_t a) {
  uint2 r; asm volatile("ld.shared.v2.u32 {%0,%1}, [%2];" : "=r"(r.x), "=r"(r.y) : "r"(a) : "memory"); return r;
}
__device__ __forceinline__ uint4 lds128(uint32_t a) {
  uint4 r;
  asm volatile("ld.shared.v4.u32 {%0,%1,%2,%3}, [%4];" : "=r"(r.x), "=r"(r.y), "=r"(r.z), "=r"(r.w) : "r"(a) : "memory");
  return r;
}
__device__ __forceinline__ void sts32(uint32_t a, uint32_t v) { asm volatile("st.shared.u32 [%0], %1;" ::"r"(a), "r"(v) : "memory"); }
__device__ __forceinline__ void sts16(uint32_t a, uint32_t v) {
  asm volatile("{\n.reg .u16 h;\ncvt.u16.u32 h, %1;\nst.shared.u16 [%0], h;\n}\n" ::"r"(a), "r"(v) : "memory");
}
__device__ __forceinline__ void sts64(uint32_t a, uint32_t x, uint32_t y) {
  asm volatile("st.shared.v2.u32 [%0], {%1,%2};" ::"r"(a), "r"(x), "r"(y) : "memory");
}
__device__ __forceinline__ void sts128(uint32_t a, uint32_t x, uint32_t y, uint32_t z, uint32_t w) {
  asm volatile("st.shared.v4.u32 [%0], {%1,%2,%3,%4};" ::"r"(a), "r"(x), "r"(y), "r"(z), "r"(w) : "memory");
}
__device__ __forceinline__ uint4 ld_x(const uint4* p) {
  uint4 r;
  asm volatile("{\n.reg .b128 t;\nld.relaxed.gpu.global.b128 t, [%4];\nmov.b128 {%0,%1,%2,%3}, t;\n}\n"
               : "=r"(r.x), "=r"(r.y), "=r"(r.z), "=r"(r.w) : "l"(p) : "memory");
  return r;
}
__device__ __forceinline__ uint32_t ld_x32(const uint32_t* p) {
  uint32_t r; asm volatile("ld.relaxed.gpu.global.u32 %0, [%1];" : "=r"(r) : "l"(p) : "memory"); return r;
}
__device__ __forceinline__ void st_x(uint4* p, uint32_t x, uint32_t y, uint32_t z, uint32_t w) {
  asm volatile("{\n.reg .b128 t;\nmov.b128 t, {%1,%2,%3,%4};\nst.relaxed.gpu.global.b128 [%0], t;\n}\n"
               ::"l"(p), "r"(x), "r"(y), "r"(z), "r"(w) : "memory");
}
__device__ __forceinline__ void st_x_p(int p, uint4* a, uint32_t x, uint32_t y, uint32_t z, uint32_t w) {
  asm volatile("{\n.reg .b128 t;\n.reg .pred q;\nsetp.ne.b32 q, %5, 0;\nmov.b128 t, {%1,%2,%3,%4};\n@q st.relaxed.gpu.global.b128 [%0], t;\n}\n"
               ::"l"(a), "r"(x), "r"(y), "r"(z), "r"(w), "r"(p) : "memory");
}
__device__ __forceinline__ void sts64_p(int p, uint32_t a, uint32_t x, uint32_t y) {
  asm volatile("{\n.reg .pred q;\nsetp.ne.b32 q, %3, 0;\n@q st.shared.v2.u32 [%0], {%1,%2};\n}\n" ::"r"(a), "r"(x), "r"(y), "r"(p) : "memory");
}
__device__ __forceinline__ void st_x32(uint32_t* p, uint32_t x) {
  asm volatile("st.relaxed.gpu.global.u32 [%0], %1;" ::"l"(p), "r"(x) : "memory");
}
__device__ __forceinline__ uint32_t nz(uint32_t w) { return max(w, 1u); }
__device__ __forceinline__ uint32_t fu(float x) { return __float_as_uint(x); }
__device__ __forceinline__ float uf(uint32_t x) { return __uint_as_float(x); }

__device__ __forceinline__ void wgmma_ss_n96(float (&d)[48], uint64_t da, uint64_t db, int sc) {
  asm volatile("{\n.reg .pred p;\nsetp.ne.b32 p, %50, 0;\n"
      "wgmma.mma_async.sync.aligned.m64n96k16.f32.bf16.bf16 "
      "{%0,%1,%2,%3,%4,%5,%6,%7,%8,%9,%10,%11,%12,%13,%14,%15,%16,%17,%18,%19,%20,%21,%22,%23,%24,%25,%26,%27,%28,%29,%30,%31,%32,%33,%34,%35,%36,%37,%38,%39,%40,%41,%42,%43,%44,%45,%46,%47}, "
      "%48, %49, p, 1, 1, 0, 1;\n}\n"
      : "+f"(d[0]), "+f"(d[1]), "+f"(d[2]), "+f"(d[3]), "+f"(d[4]), "+f"(d[5]), "+f"(d[6]), "+f"(d[7]),
        "+f"(d[8]), "+f"(d[9]), "+f"(d[10]), "+f"(d[11]), "+f"(d[12]), "+f"(d[13]), "+f"(d[14]), "+f"(d[15]),
        "+f"(d[16]), "+f"(d[17]), "+f"(d[18]), "+f"(d[19]), "+f"(d[20]), "+f"(d[21]), "+f"(d[22]), "+f"(d[23]),
        "+f"(d[24]), "+f"(d[25]), "+f"(d[26]), "+f"(d[27]), "+f"(d[28]), "+f"(d[29]), "+f"(d[30]), "+f"(d[31]),
        "+f"(d[32]), "+f"(d[33]), "+f"(d[34]), "+f"(d[35]), "+f"(d[36]), "+f"(d[37]), "+f"(d[38]), "+f"(d[39]),
        "+f"(d[40]), "+f"(d[41]), "+f"(d[42]), "+f"(d[43]), "+f"(d[44]), "+f"(d[45]), "+f"(d[46]), "+f"(d[47])
      : "l"(da), "l"(db), "r"(sc));
}

__device__ __forceinline__ void wgmma_ss_n128(float (&d)[64], uint64_t da, uint64_t db, int sc) {
  asm volatile("{\n.reg .pred p;\nsetp.ne.b32 p, %66, 0;\n"
      "wgmma.mma_async.sync.aligned.m64n128k16.f32.bf16.bf16 "
      "{%0,%1,%2,%3,%4,%5,%6,%7,%8,%9,%10,%11,%12,%13,%14,%15,%16,%17,%18,%19,%20,%21,%22,%23,%24,%25,%26,%27,%28,%29,%30,%31,%32,%33,%34,%35,%36,%37,%38,%39,%40,%41,%42,%43,%44,%45,%46,%47,%48,%49,%50,%51,%52,%53,%54,%55,%56,%57,%58,%59,%60,%61,%62,%63}, "
      "%64, %65, p, 1, 1, 0, 1;\n}\n"
      : "+f"(d[0]), "+f"(d[1]), "+f"(d[2]), "+f"(d[3]), "+f"(d[4]), "+f"(d[5]), "+f"(d[6]), "+f"(d[7]),
        "+f"(d[8]), "+f"(d[9]), "+f"(d[10]), "+f"(d[11]), "+f"(d[12]), "+f"(d[13]), "+f"(d[14]), "+f"(d[15]),
        "+f"(d[16]), "+f"(d[17]), "+f"(d[18]), "+f"(d[19]), "+f"(d[20]), "+f"(d[21]), "+f"(d[22]), "+f"(d[23]),
        "+f"(d[24]), "+f"(d[25]), "+f"(d[26]), "+f"(d[27]), "+f"(d[28]), "+f"(d[29]), "+f"(d[30]), "+f"(d[31]),
        "+f"(d[32]), "+f"(d[33]), "+f"(d[34]), "+f"(d[35]), "+f"(d[36]), "+f"(d[37]), "+f"(d[38]), "+f"(d[39]),
        "+f"(d[40]), "+f"(d[41]), "+f"(d[42]), "+f"(d[43]), "+f"(d[44]), "+f"(d[45]), "+f"(d[46]), "+f"(d[47]),
        "+f"(d[48]), "+f"(d[49]), "+f"(d[50]), "+f"(d[51]), "+f"(d[52]), "+f"(d[53]), "+f"(d[54]), "+f"(d[55]),
        "+f"(d[56]), "+f"(d[57]), "+f"(d[58]), "+f"(d[59]), "+f"(d[60]), "+f"(d[61]), "+f"(d[62]), "+f"(d[63])
      : "l"(da), "l"(db), "r"(sc));
}

__device__ __forceinline__ void wgmma_ss_n40(float (&d)[20], uint64_t da, uint64_t db, int sc) {
  asm volatile("{\n.reg .pred p;\nsetp.ne.b32 p, %22, 0;\n"
      "wgmma.mma_async.sync.aligned.m64n40k16.f32.bf16.bf16 "
      "{%0,%1,%2,%3,%4,%5,%6,%7,%8,%9,%10,%11,%12,%13,%14,%15,%16,%17,%18,%19}, "
      "%20, %21, p, 1, 1, 1, 1;\n}\n"
      : "+f"(d[0]), "+f"(d[1]), "+f"(d[2]), "+f"(d[3]), "+f"(d[4]), "+f"(d[5]), "+f"(d[6]), "+f"(d[7]),
        "+f"(d[8]), "+f"(d[9]), "+f"(d[10]), "+f"(d[11]), "+f"(d[12]), "+f"(d[13]), "+f"(d[14]), "+f"(d[15]),
        "+f"(d[16]), "+f"(d[17]), "+f"(d[18]), "+f"(d[19])
      : "l"(da), "l"(db), "r"(sc));
}

__device__ __forceinline__ void wgmma_rs_n8(float (&d)[4], const uint4& a, uint64_t db, int sc) {
  asm volatile("{\n.reg .pred p;\nsetp.ne.b32 p, %9, 0;\n"
      "wgmma.mma_async.sync.aligned.m64n8k16.f32.bf16.bf16 "
      "{%0,%1,%2,%3}, "
      "{%4,%5,%6,%7}, %8, p, 1, 1, 1;\n}\n"
      : "+f"(d[0]), "+f"(d[1]), "+f"(d[2]), "+f"(d[3])
      : "r"(a.x), "r"(a.y), "r"(a.z), "r"(a.w), "l"(db), "r"(sc));
}

__device__ __forceinline__ void wgmma_rs_n16(float (&d)[8], const uint4& a, uint64_t db, int sc) {
  asm volatile("{\n.reg .pred p;\nsetp.ne.b32 p, %13, 0;\n"
      "wgmma.mma_async.sync.aligned.m64n16k16.f32.bf16.bf16 "
      "{%0,%1,%2,%3,%4,%5,%6,%7}, "
      "{%8,%9,%10,%11}, %12, p, 1, 1, 1;\n}\n"
      : "+f"(d[0]), "+f"(d[1]), "+f"(d[2]), "+f"(d[3]), "+f"(d[4]), "+f"(d[5]), "+f"(d[6]), "+f"(d[7])
      : "r"(a.x), "r"(a.y), "r"(a.z), "r"(a.w), "l"(db), "r"(sc));
}

__device__ __forceinline__ void wgmma_rs_n24(float (&d)[12], const uint4& a, uint64_t db, int sc) {
  asm volatile("{\n.reg .pred p;\nsetp.ne.b32 p, %17, 0;\n"
      "wgmma.mma_async.sync.aligned.m64n24k16.f32.bf16.bf16 "
      "{%0,%1,%2,%3,%4,%5,%6,%7,%8,%9,%10,%11}, "
      "{%12,%13,%14,%15}, %16, p, 1, 1, 1;\n}\n"
      : "+f"(d[0]), "+f"(d[1]), "+f"(d[2]), "+f"(d[3]), "+f"(d[4]), "+f"(d[5]), "+f"(d[6]), "+f"(d[7]),
        "+f"(d[8]), "+f"(d[9]), "+f"(d[10]), "+f"(d[11])
      : "r"(a.x), "r"(a.y), "r"(a.z), "r"(a.w), "l"(db), "r"(sc));
}

struct Params {
  const __nv_bfloat16 *logA, *Aim, *Cre, *Cim, *logdt, *Dskip, *u, *x, *wphi, *wo;
  __nv_bfloat16* out;
  uint4* xs;
  long long* ts;
};

__device__ __forceinline__ uint4 tr_row(const uint4 (&v)[8], int i) {
  uint32_t o[4];
#pragma unroll
  for (int m = 0; m < 4; m++) {
    const uint4 &ra = v[2 * m], &rb = v[2 * m + 1];
    const int k = i >> 1;
    const uint32_t xa = k == 0 ? ra.x : k == 1 ? ra.y : k == 2 ? ra.z : ra.w;
    const uint32_t xb = k == 0 ? rb.x : k == 1 ? rb.y : k == 2 ? rb.z : rb.w;
    o[m] = __byte_perm(xa, xb, (i & 1) ? 0x7632 : 0x5410);
  }
  return make_uint4(o[0], o[1], o[2], o[3]);
}

struct cpx { float r, i; };
__device__ __forceinline__ cpx csq(cpx a) { return {a.r * a.r - a.i * a.i, 2.f * (a.r * a.i)}; }
__device__ __forceinline__ cpx polar(float e, float t) {
  const float m = ex2(e);
  return {m * __cosf(t), m * __sinf(t)};
}

struct KgenRaw { unsigned short la, ai, cr, ci, ldt; };
__device__ __forceinline__ KgenRaw kgen_load(const Params& P, int d, int unit, int lane) {
  const int o = d * 128 + unit * 32 + lane;
  return {__ldg((const unsigned short*)P.logA + o), __ldg((const unsigned short*)P.Aim + o), __ldg((const unsigned short*)P.Cre + o),
          __ldg((const unsigned short*)P.Cim + o), __ldg((const unsigned short*)P.logdt + d)};
}
struct hmul { __half2 a, b; };
__device__ __forceinline__ hmul mk_mul(cpx w) {
  uint32_t b;
  asm("{\n.reg .f32 n;\nneg.ftz.f32 n, %1;\ncvt.rn.f16x2.f32 %0, %2, n;\n}\n" : "=r"(b) : "f"(w.i), "f"(w.r));
  return {__floats2half2_rn(w.r, w.i), *(const __half2*)&b};
}
__device__ __forceinline__ __half2 hcm(__half2 z, const hmul& w) { return __hfma2(__high2half2(z), w.b, __hmul2(__low2half2(z), w.a)); }
__device__ __forceinline__ uint32_t hu(__half2 v) { return *(const uint32_t*)&v; }

struct KgenAddr { uint32_t sa, sb, lb, lc, la; };
__device__ __forceinline__ KgenAddr kgen_addr(int lane, uint32_t buf) {
  KgenAddr a;
  a.sa = buf + (lane & 7) * 128 + ((((lane >> 3) ^ lane) & 7) << 4);
  a.lb = buf + (lane >> 3) * 128 + (((lane ^ (lane >> 3)) & 7) << 4);
  a.la = buf + ((lane >> 3) & 1) * 1024 + (lane >> 4) * 128 + (((lane ^ (lane >> 4)) & 7) << 4);
  a.sb = a.sa ^ 64; a.lc = a.lb ^ 64;
  asm volatile("" : "+r"(a.sa), "+r"(a.sb), "+r"(a.lb), "+r"(a.lc), "+r"(a.la));
  return a;
}
__device__ __forceinline__ void kgen_unit(const KgenRaw& r, const KgenAddr& ad, uint32_t zero, float (&k)[5][4], float& k2048, float& sc) {
  const float dt = bf_round(expf(bf_lo(r.ldt)));
  const float a2 = bf_round(ex2(bf_lo(r.la) * 1.4426950408889634f)) * (dt * -1.4426950408889634f);
  const float f = bf_lo(r.ai) * dt;
  const float r128 = f * 20.371832715762604f;
  const uint32_t ex = min(max(__reduce_max_sync(0xffffffffu, max(r.cr & 0x7fffu, r.ci & 0x7fffu)) >> 7, 1u), 253u);
  const float cs = uf((254u - ex) << 23);
  sc = 2.f * dt * uf(ex << 23);
  const cpx C = {bf_lo(r.cr) * cs, -bf_lo(r.ci) * cs};
  auto put = [&](const __half2 (&v)[8], uint32_t off) {
    stsm4(ad.sa + off, hu(v[0]), hu(v[1]), hu(v[2]), hu(v[3]));
    stsm4(ad.sb + off, hu(v[4]), hu(v[5]), hu(v[6]), hu(v[7]));
  };
  uint32_t A[4][4], B[5][2][4];
  auto get = [&](int j, uint32_t off) {
    __syncwarp();
    ldsm4(B[j][0], ad.lb + off);
    ldsm4(B[j][1], ad.lc + 512 + off);
  };
  auto tile = [&](int j) {
    k[j][0] = k[j][1] = k[j][2] = k[j][3] = 0.f;
#pragma unroll
    for (int s = 0; s < 4; s++) mma_h(k[j], A[s], B[j][s >> 1][2 * (s & 1)], B[j][s >> 1][2 * (s & 1) + 1]);
  };
  auto after = [&](cpx v, uint32_t dep) { return cpx{uf(fu(v.r) ^ (dep & zero)), v.i}; };
  const cpx w1 = polar(a2, f), w128 = polar(a2 * 128.f, (r128 - rintf(r128)) * 6.283185307179586f);
  const cpx w2 = csq(w1), w4 = csq(w2);
  __half2 t0[8], t1[8], t2[8], t3[8], t4[8];
  const hmul m2 = mk_mul(w2), m4 = mk_mul(w4), m128 = mk_mul(w128);
  t0[0] = __floats2half2_rn(1.f, 0.f); t0[1] = __floats2half2_rn(w1.r, w1.i); t0[2] = m2.a; t0[4] = m4.a;
  t0[3] = hcm(t0[1], m2); t0[5] = hcm(t0[1], m4); t0[6] = hcm(t0[2], m4); t0[7] = hcm(t0[3], m4);
  put(t0, 0); get(0, 0);
  t1[0] = m128.a;
#pragma unroll
  for (int i = 1; i < 8; i++) t1[i] = hcm(t0[i], m128);
  put(t1, 1024); get(1, 1024);
  {
    cpx w8 = csq(after(w4, B[0][0][0]));
    w8.i = -w8.i;
    const cpx w16 = csq(w8), w32 = csq(w16), w64 = csq(w32);
    const hmul m8 = mk_mul(w8), m16 = mk_mul(w16), m32 = mk_mul(w32), m64 = mk_mul(w64);
    __half2 a[8];
    a[0] = __floats2half2_rn(C.r, C.i); a[1] = hcm(a[0], m8);
    a[2] = hcm(a[0], m16); a[3] = hcm(a[1], m16);
#pragma unroll
    for (int i = 0; i < 4; i++) a[4 + i] = hcm(a[i], m32);
    put(a, 0);
#pragma unroll
    for (int i = 0; i < 8; i++) a[i] = hcm(a[i], m64);
    put(a, 1024);
    __syncwarp();
#pragma unroll
    for (int s = 0; s < 4; s++) ldsm4(A[s], (ad.la ^ (s << 5)) + s * 256);
  }
  const cpx w256 = csq(after(w128, B[1][0][0]));
  const hmul m256 = mk_mul(w256);
  t2[0] = m256.a;
#pragma unroll
  for (int i = 1; i < 8; i++) t2[i] = hcm((i & 1) ? t1[i & 6] : t0[i & 6], m256);
  put(t2, 0); get(2, 0);
  tile(0); tile(1);
  const cpx w512 = csq(after(w256, A[0][0]));
  const hmul m512 = mk_mul(w512);
  t3[0] = m512.a;
#pragma unroll
  for (int i = 1; i < 8; i++) t3[i] = hcm((i & 2) ? t2[i & 5] : ((i & 1) ? t1[i & 4] : t0[i & 4]), m512);
  put(t3, 1024); get(3, 1024);
  tile(2);
  const cpx w1024 = csq(after(w512, B[2][0][0])), we = csq(w1024);
  const hmul m1024 = mk_mul(w1024);
  t4[0] = m1024.a;
#pragma unroll
  for (int i = 1; i < 8; i++) t4[i] = hcm((i & 4) ? t3[i & 3] : ((i & 2) ? t2[i & 1] : t1[0]), m1024);
  put(t4, 0); get(4, 0);
  tile(3); tile(4);
  k2048 = (C.r * we.r + C.i * we.i) * sc;
}

__device__ __forceinline__ void build_tables(uint32_t tb, int lane, float (&k)[5][4], float k2048) {
  const int g = lane >> 2, c = lane & 3;
  const uint32_t kc = tb + T_KC + 16;
  {
    const uint32_t a0 = kc + 16 * g + 4 * c, a2 = kc + 2 * (256 + 4 * g + c);
    const uint32_t a3 = kc + 2 * (384 + 2 * g + 64 * (c & 1) + (c >> 1)), a4 = kc + 2 * (512 + g + 32 * c);
#pragma unroll
    for (int r = 0; r < 2; r++) {
      sts32(a0 + 128 * r, pack_bf(k[0][2 * r], k[0][2 * r + 1]));
      sts32(a0 + 128 * r + 256, pack_bf(k[1][2 * r], k[1][2 * r + 1]));
      const uint32_t w2 = pack_bf(k[2][2 * r], k[2][2 * r + 1]);
      const uint32_t w3 = pack_bf(k[3][2 * r], k[3][2 * r + 1]);
      const uint32_t w4 = pack_bf(k[4][2 * r], k[4][2 * r + 1]);
      sts16(a2 + 64 * r, w2); sts16(a2 + 64 * r + 128, w2 >> 16);
      sts16(a3 + 32 * r, w3); sts16(a3 + 32 * r + 64, w3 >> 16);
      sts16(a4 + 16 * r, w4); sts16(a4 + 16 * r + 32, w4 >> 16);
    }
  }
  if (lane == 0) { sts16(kc + 2 * 640, pack_bf(k2048, 0.f)); sts32(kc - 4, 0); }
  __syncwarp();
  const uint32_t td = tb + T_D + 32;
#pragma unroll
  for (int hf = 0; hf < 2; hf++) {
    const uint2 v = lds64(kc + 256 * hf + 8 * lane);
    const uint32_t pv = lds32(kc + 256 * hf + 8 * lane - 4);
    sts128(td + 512 * hf + 16 * lane, __byte_perm(v.x, pv, 0x7610), __byte_perm(v.x, v.x, 0x1032), __byte_perm(v.y, v.x, 0x7610),
           __byte_perm(v.y, v.y, 0x1032));
  }
#pragma unroll
  for (int hf = 0; hf < 2; hf++) {
    const uint32_t v = lds32(kc + 512 + 128 * hf + 4 * lane), nx = lds32(kc + 516 + 128 * hf + 4 * lane);
    uint32_t w0 = __byte_perm(v, v, 0x1010);
    const uint32_t w1 = w0;
    if (hf == 0) { const uint32_t pv = lds32(kc + 508); if (lane == 0) w0 = __byte_perm(v, pv, 0x7610); }
    sts128(td + 1024 + 512 * hf + 16 * lane, w0, w1, __byte_perm(v, v, 0x1032), __byte_perm(nx, v, 0x7610));
  }
  {
    const uint32_t kk = lds16(kc + 2 * 384);
    const uint32_t w = lane < 3 ? (kk | (kk << 16)) : (lane == 3 ? (kk << 16) : 0u);
    if (lane < 24) sts32(td + 4 * (lane < 16 ? 512 + lane : lane - 24), w);
    const uint32_t lo_ = lds16(kc + 2 * 511), le_ = lds16(kc + 2 * 512);
    const uint32_t ja = tb + T_5 + (lane < 16 ? 4 * lane : 256 + 4 * lane);
    sts32(ja, lane == 16 ? (le_ << 16) : 0u);
    sts32(ja + 384, lane == 16 ? (lo_ << 16) : 0u);
    sts32(tb + (lane < 16 ? T_7 : T_9 - 64) + 4 * lane, 0u);
  }
#pragma unroll
  for (int s = 0; s < 2; s++) {
    const uint32_t b = kc + 2 * (s ? 512 : 384) + 8 * lane;
    const uint2 v = lds64(b);
    uint32_t em = lds16(b - 2), e0 = v.x;
    const uint32_t e4 = lds16(b + 8);
    if (lane == 0) { em = 0; e0 = 0; }
    sts64(tb + (s ? T_7 : T_3) + 64 + 8 * lane, __byte_perm(v.x, em, 0x5432), __byte_perm(v.y, v.x, 0x7632));
    sts64(tb + (s ? T_9 : T_5) + 64 + 8 * lane, __byte_perm(v.y, e0, 0x5410), __byte_perm(e4, v.y, 0x5410));
  }
  __syncwarp();
}

__device__ __forceinline__ uint32_t box2w(int lo, int n, int o) {
  return ((unsigned)(o - lo) < (unsigned)n ? 0x3F80u : 0u) | ((unsigned)(o + 1 - lo) < (unsigned)n ? 0x3F800000u : 0u);
}

__device__ __forceinline__ void conv_channel(uint32_t ub, uint32_t tb, int lane, uint4* ydst) {
  const int g = lane >> 2, c = lane & 3, x = g - 2 * c;
  const int mi = lane >> 3;
  const uint32_t qa = ub + U_PAD + 16 * (lane & 7) + ((mi == 0 || mi == 3) ? U_ODD : 0) - (mi == 0 ? 16 : 0);
  const uint32_t hb = ub + U_PAD + (mi & 1) * U_ODD + 16 * ((lane >> 4) + (lane & 7)) - 16;
  const uint32_t kv = lds16(tb + T_KC + 16 + 2 * 512);
  const int oh = c < 2 ? 8 + 2 * c : 2 * c - 8, og = c < 3 ? 2 * c : -10;
  uint32_t bx[4] = {box2w(g - 4, 9, 2 * c), box2w(g - 3, 7, 2 * c), box2w(g - 4, 9, oh), box2w(g - 3, 7, oh)};
  uint32_t by[4] = {box2w(g - 10, 5, 2 * c - 8), box2w(g - 5, 3, 2 * c - 8), box2w(g - 10, 5, og), box2w(g - 5, 3, og)};
  uint32_t lb0 = ((unsigned)(x + 5) < 2u ? kv : 0u) | ((unsigned)(x + 4) < 2u ? kv << 16 : 0u);
  uint32_t lb1 = ((unsigned)(x - 3) < 2u ? kv : 0u) | ((unsigned)(x - 4) < 2u ? kv << 16 : 0u);
  const int q0 = g - 1, q1 = c < 3 ? g : g - 2;
  uint32_t y0a = ub + U_PAD + (q0 & 1) * U_ODD + 16 * (q0 >> 1) + 4 * c;
  uint32_t y1a = ub + U_PAD + (q1 & 1) * U_ODD + 16 * (q1 >> 1) + 4 * c;
#pragma unroll
  for (int i = 0; i < 4; i++) asm volatile("" : "+r"(bx[i]), "+r"(by[i]));
  asm volatile("" : "+r"(lb0), "+r"(lb1), "+r"(y0a), "+r"(y1a));
  mbar_wait(BAR(MB_UFULL));
  mbar_spin(BAR(MB_EMPTY + 15));
  TS(36);
  float acc[16][4];
  {
    uint32_t z09[8], z07[8], zm9[8], zm7[8];
#pragma unroll
    for (int i = 0; i < 8; i++) {
      uint32_t h[4];
      ldsm4(h, hb + 128 * i);
      float y0, y1, y2, y3, w0, w1, w2, w3;
      mma0(y0, y1, y2, y3, bx[0], bx[1], bx[2], bx[3], h[2], c < 2 ? h[3] : h[1]);
      mma0(w0, w1, w2, w3, bx[0], bx[1], bx[2], bx[3], h[1], c < 2 ? h[2] : h[0]);
      z09[i] = pack_bf(y0, y1); z07[i] = pack_bf(y2, y3);
      zm9[i] = pack_bf(w0, w1); zm7[i] = pack_bf(w2, w3);
    }
  uint32_t f3[3][4][4];
  {
    const uint32_t fa = tb + T_7 + 4 * (16 + x);
#pragma unroll
    for (int tt = 0; tt < 3; tt++)
#pragma unroll
      for (int D = 0; D < 4; D++) {
        const uint32_t a = fa + (tt == 0 ? 316 : (tt == 1 ? 320 : 0)) + 64 * D;
        f3[tt][D][0] = lds32(a); f3[tt][D][1] = lds32(a + 32); f3[tt][D][2] = lds32(a - 32); f3[tt][D][3] = lds32(a);
      }
  }
    float a[4][2][4];
#pragma unroll
    for (int kap = 0; kap < 4; kap++)
#pragma unroll
      for (int sg = 0; sg < 2; sg++)
#pragma unroll
        for (int bk = 3; bk >= kap; bk--) {
          const uint32_t(&q0_)[4] = f3[sg ? 2 : 0][bk - kap];
          const uint32_t(&q1_)[4] = f3[sg ? 2 : 1][bk - kap];
          float(&a0)[4] = a[bk][0];
          float(&a1)[4] = a[bk][1];
          if (sg == 0 && kap == 0) {
            mma0(a0[0], a0[1], a0[2], a0[3], q0_[0], q0_[1], q0_[2], q0_[3], z09[0], z09[1]);
            mma0(a1[0], a1[1], a1[2], a1[3], q1_[0], q1_[1], q1_[2], q1_[3], zm9[0], zm9[1]);
          } else {
            mma(a0[0], a0[1], a0[2], a0[3], q0_[0], q0_[1], q0_[2], q0_[3], sg ? zm7[2 * kap] : z09[2 * kap], sg ? zm7[2 * kap + 1] : z09[2 * kap + 1]);
            mma(a1[0], a1[1], a1[2], a1[3], q1_[0], q1_[1], q1_[2], q1_[3], sg ? z07[2 * kap] : zm9[2 * kap], sg ? z07[2 * kap + 1] : zm9[2 * kap + 1]);
          }
        }
    SPLIT();
#pragma unroll
    for (int i = 0; i < 8; i++) {
      uint32_t h[4];
      ldsm4(h, qa + 128 * i);
      const float ci[4] = {a[i >> 1][0][2 * (i & 1)], a[i >> 1][0][2 * (i & 1) + 1], a[i >> 1][1][2 * (i & 1)], a[i >> 1][1][2 * (i & 1) + 1]};
      mmac(acc[8 + i], h[0], h[1], h[2], h[3], lb0, lb1, ci);
    }
  }
  TS(44);
  {
    uint2 a5[10], a3[10];
    const uint32_t aa = tb + T_5 + 4 * (8 + 2 * g - 2 * c);
#pragma unroll
    for (int m = 0; m < 10; m++) { a5[m] = lds64(aa + 32 * m); a3[m] = lds64(aa + 384 + 32 * m); }
    uint32_t x5[12][2], x3[12][2];
    auto ygen = [&](int kap) {
#pragma unroll
      for (int hh = 0; hh < 2; hh++) {
        float y0, y1, y2, y3;
        mma0(y0, y1, y2, y3, by[0], by[1], by[2], by[3], lds32(y0a + 128 * kap + 64 * hh), lds32(y1a + 128 * kap + 64 * hh));
        x5[kap][hh] = pack_bf(y0, y1);
        x3[kap][hh] = pack_bf(y2, y3);
      }
    };
    ygen(11); ygen(10); ygen(9); ygen(8);
#pragma unroll
    for (int kap = 11; kap >= 0; kap--) {
      if (kap >= 4) ygen(kap - 4);
#pragma unroll
      for (int sg = 0; sg < 2; sg++)
#pragma unroll
        for (int i = 4; i >= 0; i--) {
          const int be = kap + 4 + i;
          if (be <= 15) {
            const uint2 &hi = sg ? a3[2 * i + 1] : a5[2 * i + 1], &lo = sg ? a3[2 * i] : a5[2 * i];
            const uint32_t b0 = sg ? x3[kap][0] : x5[kap][0], b1 = sg ? x3[kap][1] : x5[kap][1];
            if (be < 8 && i == 0 && sg == 0) mma0(acc[be][0], acc[be][1], acc[be][2], acc[be][3], hi.x, hi.y, lo.x, lo.y, b0, b1);
            else mma(acc[be][0], acc[be][1], acc[be][2], acc[be][3], hi.x, hi.y, lo.x, lo.y, b0, b1);
          }
        }
    }
  }
  TS(45);
  {
    const uint32_t st = tb + T_ST + lane * 8;
#pragma unroll
    for (int be = 4; be < 12; be++) sts64(st + 256 * be, pack_bf(acc[be][0], acc[be][1]), pack_bf(acc[be][2], acc[be][3]));
    SPLIT();
    uint32_t F[66], qd[8][4];
    const uint32_t fa = tb + T_D + 32 + 4 * x;
#pragma unroll
    for (int i = 0; i < 32; i++) {
      const int s = 120 - (i >> 2) - 8 * (i & 3);
      uint32_t(&q)[4] = qd[i & 7];
      ldsm4(q, qa + 16 * s);
      const int m = 16 * (i & 3) + 2 * (i >> 2);
      F[m] = lds32(fa + 32 * m); F[m + 1] = lds32(fa + 32 * m + 32);
#pragma unroll
      for (int be = 15; be >= 12; be--) {
        const int de = 8 * be - s;
        float(&a)[4] = (be >= 14 && !(i & 1)) ? acc[be - 4] : acc[be];
        if (de >= 0 && be >= 14 && i == 2 * (15 - be)) mma0(a[0], a[1], a[2], a[3], q[0], q[1], q[2], q[3], F[2 * de + 1], F[2 * de]);
        else if (de >= 0) mma(a[0], a[1], a[2], a[3], q[0], q[1], q[2], q[3], F[2 * de + 1], F[2 * de]);
      }
    }
#pragma unroll
    for (int i = 0; i < 8; i++) acc[14 + (i >> 2)][i & 3] += acc[10 + (i >> 2)][i & 3];
    F[64] = lds32(fa + 32 * 64); F[65] = lds32(fa + 32 * 65);
    uint32_t qp = qa + 128 * 11, sta = st + 256 * 10;
    uint4* yd = ydst + 7 * 32;
#pragma unroll
    for (int i = 0; i < 6; i++) ldsm4(qd[i], qp - 16 * i);
    uint2 sv = lds64(sta + 256);
    float ci[4] = {bf_lo(sv.x), bf_hi(sv.x), bf_lo(sv.y), bf_hi(sv.y)};
    float T[5][4];
#pragma unroll
    for (int i = 0; i < 16; i++) T[i >> 2][i & 3] = acc[12 + (i >> 2)][i & 3];
    nb_sync(NB_YZ, 160);
    TS(46);
#pragma unroll 1
    for (int bp = 5; bp >= 0; bp--) {
      uint32_t held[2];
#pragma unroll
      for (int o = 1; o >= 0; o--) {
#pragma unroll
        for (int k = 4; k >= 1; k--) mmac(T[k], qd[0][0], qd[0][1], qd[0][2], qd[0][3], F[16 * k + 1], F[16 * k], T[k - 1]);
        mmac(T[0], qd[0][0], qd[0][1], qd[0][2], qd[0][3], F[1], F[0], ci);
        ldsm4(qd[6], qp - 16 * 6);
        ldsm4(qd[7], qp - 16 * 7);
        sv = lds64(sta);
#pragma unroll
        for (int i = 1; i < 8; i++) {
#pragma unroll
          for (int k = 3; k >= 0; k--)
            mma(T[k][0], T[k][1], T[k][2], T[k][3], qd[i][0], qd[i][1], qd[i][2], qd[i][3], F[16 * k + 2 * i + 1], F[16 * k + 2 * i]);
          if (i < 7) ldsm4(qd[i - 1], qp - 128 - 16 * (i - 1));
          if (i == 2) {
            const uint32_t w0 = pack_bf(T[4][0], T[4][1]), w1 = pack_bf(T[4][2], T[4][3]);
            if (o) { held[0] = w0; held[1] = w1; }
            else st_x(yd, nz(w0), w1, held[0], held[1]);
          }
          if (i == 4) {
            if (2 * bp + o <= 4) sv = make_uint2(0, 0);
            ci[0] = bf_lo(sv.x); ci[1] = bf_hi(sv.x); ci[2] = bf_lo(sv.y); ci[3] = bf_hi(sv.y);
          }
        }
        qp -= 128; sta -= 256;
      }
      yd -= 32;
      if (!(bp & 1)) nb_arrive(NB_Y + 1 + (bp >> 1), 160);
    }
#pragma unroll
    for (int B = 1; B >= 0; B--)
      st_x(ydst + B * 32, nz(pack_bf(T[2 * B][0], T[2 * B][1])), pack_bf(T[2 * B][2], T[2 * B][3]),
           pack_bf(T[2 * B + 1][0], T[2 * B + 1][1]), pack_bf(T[2 * B + 1][2], T[2 * B + 1][3]));
  }
}

__device__ __forceinline__ void dual_exp(const uint32_t* w, uint32_t* e) {
  const float L = 1.44268798828125f;
  uint32_t mx = bmax2(bmax2(w[0], w[1]), bmax2(w[2], w[3]));
  uint32_t mn = bmin2(bmin2(w[0], w[1]), bmin2(w[2], w[3]));
  mx = bmax2(mx, __shfl_xor_sync(0xffffffffu, mx, 1));
  mn = bmin2(mn, __shfl_xor_sync(0xffffffffu, mn, 1));
  mx = bmax2(mx, __shfl_xor_sync(0xffffffffu, mx, 2));
  mn = bmin2(mn, __shfl_xor_sync(0xffffffffu, mn, 2));
  const float mx0 = bf_lo(mx) * -L, mx1 = bf_hi(mx) * -L, mn0 = bf_lo(mn) * L, mn1 = bf_hi(mn) * L;
#pragma unroll
  for (int i = 0; i < 2; i++) {
    const float a0 = bf_lo(w[2 * i]), a1 = bf_hi(w[2 * i]), b0 = bf_lo(w[2 * i + 1]), b1 = bf_hi(w[2 * i + 1]);
    e[2 * i] = pack_bf(ex2(fmaf(a0, L, mx0)), ex2(fmaf(b0, L, mx0)));
    e[2 * i + 1] = pack_bf(ex2(fmaf(a1, L, mx1)), ex2(fmaf(b1, L, mx1)));
    e[4 + 2 * i] = pack_bf(ex2(fmaf(a0, -L, mn0)), ex2(fmaf(b0, -L, mn0)));
    e[5 + 2 * i] = pack_bf(ex2(fmaf(a1, -L, mn1)), ex2(fmaf(b1, -L, mn1)));
  }
}
__device__ __forceinline__ void normalise(uint32_t* e, const float (&s)[4]) {
  const uint32_t r = pack_bf(rcp(s[0]), rcp(s[2]));
  const __nv_bfloat162 rr = *(const __nv_bfloat162*)&r;
#pragma unroll
  for (int i = 0; i < 4; i++) {
    const __nv_bfloat162 v = __hmul2(*(const __nv_bfloat162*)&e[i], (i & 1) ? __high2bfloat162(rr) : __low2bfloat162(rr));
    e[i] = *(const uint32_t*)&v;
  }
}
__host__ __device__ constexpr uint64_t qdesc(uint32_t addr) { return mkdesc(addr, 128, 256, 0); }

__global__ void __launch_bounds__(NTHREADS, 1)
fused_kernel(const Params P, const __grid_constant__ CUtensorMap mx, const __grid_constant__ CUtensorMap mw,
             const __grid_constant__ CUtensorMap mo, const __grid_constant__ CUtensorMap mout,
             const __grid_constant__ CUtensorMap mw4) {
  constexpr uint32_t sb = SB;
  const int tid = threadIdx.x, lane = tid & 31;
  const int warp = __shfl_sync(0xffffffffu, tid >> 5, 0);
  const int b = blockIdx.x, oct = b >> 3, i8 = b & 7;
  const int rt = (((oct & 4) ? ~oct : oct) & 3) * 2 + (i8 >> 2);
  const int hp = (oct >> 2) * 4 + (i8 & 3);

  const int wg = warp >> 2, w = warp & 3;
  const int d = b * 4 + ((tid >> 5) & 3);
  if (warp == 15) {
    asm volatile("prefetch.tensormap [%0];" ::"l"(&mw) : "memory");
    asm volatile("prefetch.tensormap [%0];" ::"l"(&mx) : "memory");
    asm volatile("prefetch.tensormap [%0];" ::"l"(&mw4) : "memory");
  } else if (warp == 12) {
    if (lane == 0) {
#pragma unroll
      for (int i = 1; i < 9; i++) mbar_init(BAR(i), 1);
      asm volatile("fence.mbarrier_init.release.cluster;" ::: "memory");
    }
    __syncwarp();
    if (lane < 8) mbar_expect(BAR(MB_FULL) + 8 * lane, lane < 4 ? 28672 : ((lane & 1) ? 16384 : 40960));
    __syncwarp();
    e_tma3d(sb + OFF_W, &mw, BAR(MB_FULL), hp * 32, 0, 0);
    e_tma2d(sb + OFF_X + 3 * 16384, &mx, BAR(MB_FULL), 0, rt * 256);
  }
  const KgenRaw raw = kgen_load(P, d, tid >> 7, lane);
  const unsigned short dsk = __ldg((const unsigned short*)P.Dskip + d);
  if (wg == 1) {
    const __nv_bfloat16* src = P.u + (size_t)(oct * 128 + (w >> 1) * 64 + (w & 1) * 8 + (lane >> 3) * 16) * 512 + i8 * 64 + (lane & 7) * 8;
    const uint32_t dst = sb + OFF_STG0 + w * 4096 + (lane >> 3) * 128 + (((lane ^ (lane >> 3)) & 7) << 4);
#pragma unroll
    for (int i = 0; i < 8; i++)
      asm volatile("cp.async.cg.shared.global [%0], [%1], 16;" ::"r"((dst ^ ((i & 1) << 6)) + i * 512), "l"(src + i * 512) : "memory");
  } else if (warp == 14) {
    e_prefetch(P.x + (size_t)(rt * 256 + hp * 8) * 512, 8192);
  } else if (warp == 13) {
    if (lane == 0) {
#pragma unroll
      for (int i = 9; i < 39; i++) mbar_init(BAR(i), i < MB_EMPTY ? 1 : (i < MB_AUX ? 4 : 8));
      asm volatile("fence.mbarrier_init.release.cluster;" ::: "memory");
    }
    __syncwarp();
    if (lane < 13 && lane != 9) mbar_expect(BAR(MB_FULL + 8) + 8 * lane, lane < 8 ? 16384 : (lane == 8 ? 131072 : (lane == 10 ? 8192 : (lane == 11 ? 24576 : 32768))));
    nb_arrive(NB_PROD, 160);
  }
  const uint32_t tb = sb + OFF_T + w * T_CH;
  const uint32_t kp = wg >= 2 ? sb + OFF_STG0 + 16384 + w * 2048 : ((tb + 127) & ~127u) + wg * 2048;
  const KgenAddr kad = kgen_addr(lane, wg == 3 ? sb + OFF_X + 32768 + w * 2048 : kp);
  if (wg == 1) nb_sync(NB_PROD, 160);
  if (warp == 12) {
#pragma unroll 1
    for (int kb = 1; kb < 4; kb++) {
      e_tma3d(sb + OFF_W + kb * 12288, &mw, BAR(MB_FULL) + 8 * kb, hp * 32, kb * 64, 0);
      e_tma2d(sb + OFF_X + (kb < 2 ? kb + 3 : kb - 2) * 16384, &mx, BAR(MB_FULL) + 8 * kb, kb * 64, rt * 256);
    }
    e_tma4d(sb + OFF_W + 4 * 12288, &mw4, BAR(MB_FULL + 4), hp * 32, 4);
    e_tma4d(sb + OFF_W + 6 * 12288, &mw4, BAR(MB_FULL + 6), hp * 32, 6);
    if (smem_u32(smem_raw) != SB) __trap();
    if (lane == 0) TS1(54);
  }
  float k[5][4], k2048, ksc;
  kgen_unit(raw, kad, blockIdx.y, k, k2048, ksc);
  TS(40 + wg);
  if ((fu(k[0][0]) & fu(k[1][0]) & fu(k[2][0]) & fu(k[3][0]) & fu(k[4][0])) == 0xffffffffu) sts32(kp, 0);
  if (wg == 3) {
    nb_sync(0, 512);
    if (warp == 12) {
      asm volatile("fence.proxy.async.shared::cta;" ::: "memory");
      e_tma2d(sb + OFF_X + 2 * 16384, &mx, BAR(MB_FULL + 4), 256, rt * 256);
      if (X2_AT < 0) e_prefetch(P.x + (size_t)(rt * 256 + 128 + hp * 8) * 512, 8192);
    }
  } else if (wg) {
    nb_arrive(0, 512);
  }
  k2048 += __shfl_xor_sync(0xffffffffu, k2048, 16);
  k2048 += __shfl_xor_sync(0xffffffffu, k2048, 8);
  if (wg != 2) {
    uint32_t h[10];
#pragma unroll
    for (int j = 0; j < 10; j++) h[j] = hu(__floats2half2_rn(k[j >> 1][2 * (j & 1)], k[j >> 1][2 * (j & 1) + 1]));
    sts128(kp + lane * 16, h[0], h[1], h[2], h[3]);
    sts128(kp + 512 + lane * 16, h[4], h[5], h[6], h[7]);
    sts128(kp + 1024 + lane * 16, h[8], h[9], fu(k2048), fu(ksc));
  }
  if (wg == 0) { nb_arrive(NB_PREP, 512); nb_sync(0, 512); }
  else if (wg != 2) nb_arrive(NB_PREP, 512);
  else nb_sync(NB_PREP, 512);
  if (warp >= 12) {
    asm volatile("setmaxnreg.dec.sync.aligned.u32 32;");
    if (warp == 12) {
      uint32_t slot = sb + OFF_X + 3 * 16384;
#pragma unroll 1
      for (int n = 0; n < 11; n++) {
        mbar_spin(BAR(MB_EMPTY) + 8 * n);
        const int m = n + 5;
        e_tma2d(slot, &mx, BAR(MB_FULL) + 8 * m, (m & 7) * 64, rt * 256 + (m >> 3) * 128);
        slot = slot == sb + OFF_X + 4 * 16384 ? sb + OFF_X : slot + 16384;
        if (n == X2_AT) e_prefetch(P.x + (size_t)(rt * 256 + 128 + hp * 8) * 512, 8192);
        if (n == 7) {
          e_prefetch(P.wo + (size_t)b * 2048, 4096);
          asm volatile("prefetch.tensormap [%0];" ::"l"(&mo) : "memory");
          asm volatile("prefetch.tensormap [%0];" ::"l"(&mout) : "memory");
        }
      }
#pragma unroll 1
      for (int i = 0; i < 8; i++) {
        mbar_wait(BAR(MB_EMPTY + 10) + 8 * ((0x54332222u >> (4 * i)) & 7));
        const int w0 = (0x54736210u >> (4 * i)) & 7;
        e_tma3d(sb + OFF_W + w0 * 16384, &mo, BAR(MB_WO), 0, w0 * 64, (hp & 3) * 2);
      }
    } else {
      if (warp == 15) {
        const uint4 v0 = __ldg((const uint4*)P.wphi + hp * 64 + lane), v1 = __ldg((const uint4*)P.wphi + hp * 64 + 32 + lane);
        sts128(sb + OFF_PHI + (lane & 1) * 256 + (lane >> 1) * 16, v0.x, v0.y, v0.z, v0.w);
        sts128(sb + OFF_PHI + 512 + (lane & 1) * 256 + (lane >> 1) * 16, v1.x, v1.y, v1.z, v1.w);
        const uint32_t one = (((lane >> 3) ^ (lane >> 4)) & 1) ? 0u : ((lane & 1) ? 0x3F800000u : 0x3F80u);
        const int q = (lane >> 1) & 3;
        sts128(sb + OFF_EYE + lane * 16, q == 0 ? one : 0u, q == 1 ? one : 0u, q == 2 ? one : 0u, q == 3 ? one : 0u);
        sts64(sb + OFF_ONE + lane * 8, 0x3F803F80u, 0x3F803F80u);
        asm volatile("fence.proxy.async.shared::cta;" ::: "memory");
        nb_arrive(NB_KREAD, 160);
      }
      uint32_t* cnt = (uint32_t*)(P.xs + X_CNT) + (warp == 13 ? i8 : (warp == 14 ? 8 + rt : 16 + oct)) * 32;
      const unsigned target = (ld_x32(cnt) & ~15u) + 16;
      if (warp != 14) {
        if (warp == 15) mbar_wait(BAR(MB_EMPTY + ZERO_STEP));
        uint4* pz = P.xs + (warp == 13 ? X_PART + (hp * 8 + rt) * 144 : X_Y + b * 1024) + lane;
#pragma unroll 1
        for (int i = (warp == 13 ? 144 : 1024) - lane; i > 0; i -= 32, pz += 32) st_x(pz, 0, 0, 0, 0);
      }
      if (warp == 15) __syncwarp();
      else nb_sync(warp == 13 ? NB_INIT : NB_ODONE, warp == 13 ? 160 : 288);
      if (lane == 0) asm volatile("red.release.gpu.global.add.u32 [%0], %1;" ::"l"(cnt), "r"(warp == 15 ? 2 : 1) : "memory");
      if (lane == 0) TS1(warp == 13 ? 50 : (warp == 14 ? 57 : 53));
      asm volatile("fence.proxy.async.shared::cta;" ::: "memory");
      if (warp == 13) cnt += ((lane & 1 ? b >> 4 : i8 ^ (lane & 4)) - i8) * 32;
#pragma unroll 1
      for (int i = 0; i < SPIN_MAX; i++) {
        unsigned v;
        asm volatile("ld.acquire.gpu.global.u32 %0, [%1];" : "=r"(v) : "l"(cnt) : "memory");
        if (__all_sync(0xffffffffu, (int)(v - target) >= 0)) break;
      }
      if (lane == 0) TS1(warp == 13 ? 51 : (warp == 14 ? 58 : 55));
      if (warp == 15) { nb_arrive(NB_YZ, 160); return; }
      asm volatile("fence.proxy.async.global;" ::: "memory");
      if (warp == 13) {
        mbar_wait(BAR(MB_EMPTY + 11));
        e_expect(BAR(MB_UFULL), 4 * U_CH);
        e_bulk(sb + OFF_U, P.xs + X_UT + b * (U_CH / 4), 4 * U_CH, BAR(MB_UFULL));
      } else {
        const uint4* src = P.xs + X_O + (rt * 4 + (hp >> 2)) * 4096;
        e_bulk(sb + OFF_X + 32768 + 57344, src + 3584, 8192, BAR(MB_OA));
        e_bulk(sb + OFF_X + 32768, src, 32768, BAR(MB_OC));
        e_bulk(sb + OFF_STG0, src + 3200, 6144, BAR(MB_OB));
        nb_sync(NB_BDONE, 288);
        asm volatile("fence.proxy.async.shared::cta;" ::: "memory");
        e_bulk(sb + OFF_U, src + 2048, 18432, BAR(MB_OB));
      }
    }
    return;
  }

  const int t = tid & 127;
  const int g = lane >> 2, c = lane & 3;
  if (wg == 1) {
    asm volatile("cp.async.wait_all;" ::: "memory");
    __syncwarp();
    TS(48);
    uint4* dst = P.xs + X_UT + (i8 * 64 + g) * (U_CH / 16) + (w & 1) * (U_ODD / 16) + U_PAD / 16 + oct * 8 + (w >> 1) * 4 + c;
    const int ln = ((lane >> 1) & 3) + 4 * (lane & 1);
    uint32_t r[8][4];
#pragma unroll
    for (int i = 0; i < 8; i++) ldsm4t(r[i], sb + OFF_STG0 + w * 4096 + ((lane >> 3) * 8 + ln) * 128 + ((i ^ ln) << 4));
#pragma unroll
    for (int i = 0; i < 8; i++) dst[i * (U_CH / 2)] = make_uint4(r[i][0], r[i][1], r[i][2], r[i][3]);
    nb_arrive(NB_INIT, 160);
    if (lane == 0) mbar_arrive(BAR(MB_AUX));
  }
  {
    if (wg == 2) {
      asm volatile("setmaxnreg.inc.sync.aligned.u32 160;");
#pragma unroll
      for (int j = 0; j < 5; j++) { k[j][0] *= ksc; k[j][1] *= ksc; k[j][2] *= ksc; k[j][3] *= ksc; }
#pragma unroll 1
      for (int q = 0; q < 3; q++) {
        const uint32_t src = (q == 2 ? kp : ((tb + 127) & ~127u) + q * 2048) + lane * 16;
        const uint4 v0 = lds128(src), v1 = lds128(src + 512), v2 = lds128(src + 1024);
        const uint32_t h[10] = {v0.x, v0.y, v0.z, v0.w, v1.x, v1.y, v1.z, v1.w, v2.x, v2.y};
#pragma unroll
        for (int j = 0; j < 10; j++) {
          const float2 f = __half22float2(*(const __half2*)&h[j]);
          k[j >> 1][2 * (j & 1)] = fmaf(f.x, uf(v2.w), k[j >> 1][2 * (j & 1)]);
          k[j >> 1][2 * (j & 1) + 1] = fmaf(f.y, uf(v2.w), k[j >> 1][2 * (j & 1) + 1]);
        }
        k2048 += uf(v2.z);
      }
#pragma unroll
      for (int o2 = 4; o2; o2 >>= 1) k2048 += __shfl_xor_sync(0xffffffffu, k2048, o2);
      if (lane == 0) k[0][0] += bf_lo(dsk);
      __syncwarp();
      if (lane == 0) mbar_arrive(BAR(MB_AUX));
      TS(34);
      build_tables(tb, lane, k, k2048);
      TS(35);
      uint4* const g_y = P.xs + X_Y;
      conv_channel(sb + OFF_U + w * U_CH, tb, lane, g_y + (size_t)d * 256 + lane);
      nb_arrive(NB_BDONE, 288);
      nb_arrive(NB_Y, 160);
      TS(37);
      if (w == 0) TSDUMP(32);
      return;
    }
    if (wg == 1) {
      mbar_wait(BAR(MB_EMPTY + 4));
      mbar_spin(BAR(MB_EMPTY + 6));
    }
    TS(wg * 16 + 1);
  }

  float acc[2][48];
  {
    uint32_t fb = BAR(MB_FULL) + 64 * wg;
    uint32_t da = (uint32_t)mkdesc(sb + OFF_X, 16, 0, 0) + (wg ? 1024 : 3072), db = (uint32_t)mkdesc(sb + OFF_W, 4096, 0, 0);
    constexpr uint64_t ha = mkdesc(0, 0, 1024, 1), hb = mkdesc(0, 0, 512, 2);
    mbar_spin(fb);
    TS(wg * 16 + 2);
#pragma unroll 1
    for (int kb = 0; kb < 8; kb++) {
      WG_FENCE();
#pragma unroll
      for (int k = 0; k < 4; k++) {
        wgmma_ss_n96(acc[0], ha | (da + 2 * k), hb | (db + 64 * k), k ? 1 : kb);
        wgmma_ss_n96(acc[1], ha | (da + 2 * k + 512), hb | (db + 64 * k), k ? 1 : kb);
      }
      WG_COMMIT();
      if (kb < 7) mbar_spin(fb + 8);
      WG_WAIT(1);
      if (kb > 0) e_arrive(fb + 8 * (MB_EMPTY - MB_FULL - 1));
      fb += 8; db += 768;
      da = da == (uint32_t)mkdesc(sb + OFF_X + 65536, 16, 0, 0) ? da - 4096 : da + 1024;
    }
    if (wg == 0) nb_sync(NB_KREAD, 160);
    asm volatile("setmaxnreg.inc.sync.aligned.u32 160;");
    WG_WAIT(0);
    e_arrive(fb + 8 * (MB_EMPTY - MB_FULL - 1));
    SPLIT();
  }
  TS(wg * 16 + 3);

  constexpr uint32_t stg0 = sb + OFF_STG0, stg1 = sb + OFF_X + 32768;
  uint4* const g_part = P.xs + X_PART;
  uint4* const g_o = P.xs + X_O;
  constexpr uint32_t kvs = stg0;
  auto pack8 = [](const float* a) { return make_uint4(pack_bf(a[0], a[1]), pack_bf(a[2], a[3]), pack_bf(a[4], a[5]), pack_bf(a[6], a[7])); };
  auto feat = [&](const uint4 (&af)[4], float (&p)[4][8]) {
    WG_FENCE();
#pragma unroll
    for (int u = 0; u < 4; u++) wgmma_rs_n16(p[u], af[u], qdesc(sb + OFF_PHI + (u & 1) * 512), 0);
    WG_COMMIT();
  };
  auto packp = [](const float (&p)[4][8], uint32_t (&pw)[16]) {
#pragma unroll
    for (int i = 0; i < 16; i++) pw[i] = pack_bf(p[i >> 2][(i & 1) + 2 * (i & 2)], p[i >> 2][(i & 1) + 2 * (i & 2) + 2]);
  };
  auto contract = [&](float (&kc)[20], uint32_t stg, int acc_in) {
    WG_FENCE();
#pragma unroll
    for (int s = 0; s < 8; s++) wgmma_ss_n40(kc, qdesc(stg + s * SLAB), qdesc(stg + s * SLAB + 2048), s ? 1 : acc_in);
    WG_COMMIT();
    WG_WAIT(0);
  };
  uint32_t eq[32];
  {
    uint4 af[4], aq[4], vp[4];
    float p[4][8];
#pragma unroll
    for (int u = 0; u < 4; u++) af[u] = pack8(acc[u >> 1] + 16 + 8 * (u & 1));
    feat(af, p);
#pragma unroll
    for (int u = 0; u < 4; u++) { aq[u] = pack8(acc[u >> 1] + 8 * (u & 1)); vp[u] = pack8(acc[u >> 1] + 32 + 8 * (u & 1)); }
    WG_WAIT(0);
    uint32_t pw[16], ek[32];
    packp(p, pw);
#pragma unroll
    for (int u = 0; u < 4; u++) dual_exp(pw + 4 * u, ek + 8 * u);
    TS(wg * 16 + 12);
    mbar_spin(wg ? BAR(MB_EMPTY + 15) : BAR(MB_AUX));
    float rs[8][4];
    WG_FENCE();
#pragma unroll
    for (int i = 0; i < 8; i++) wgmma_rs_n8(rs[i], make_uint4(ek[4 * i], ek[4 * i + 1], ek[4 * i + 2], ek[4 * i + 3]), qdesc(sb + OFF_ONE), 0);
    WG_COMMIT();
    feat(aq, p);
    const uint32_t sl = (wg ? stg1 : stg0) + w * SLAB + lane * 16;
#pragma unroll
    for (int i = 0; i < 4; i++) stsm4(sl + (i >> 1) * 4 * SLAB + 2048 + (i & 1) * 512, vp[i].x, vp[i].y, vp[i].z, vp[i].w);
    sts128(sl + (lane >> 4) * (4 * SLAB - 256) + 3072, 0x3F803F80u, 0x3F803F80u, 0x3F803F80u, 0x3F803F80u);
    WG_WAIT(1);
#pragma unroll
    for (int i = 0; i < 8; i++) {
      normalise(ek + 4 * i, rs[i]);
      stsm4(sl + (i >> 2) * 4 * SLAB + (i & 3) * 512, ek[4 * i], ek[4 * i + 1], ek[4 * i + 2], ek[4 * i + 3]);
    }
    asm volatile("fence.proxy.async.shared::cta;" ::: "memory");
    TS(wg * 16 + 13);
    if (wg) {
      nb_arrive(NB_ST0, 256);
    } else {
      float kc[20];
      uint4* pp = g_part + (size_t)(hp * 8 + rt) * 144 + t;
      uint32_t* pz = (uint32_t*)(pp - t + 128) + w * 16 + c * 8 + g;
      asm volatile("" : "+l"(pp), "+l"(pz));
      nb_sync(NB_WG0, 128);
      contract(kc, stg0, 0);
      mbar_wait(BAR(MB_UFULL));
      TS(15);
      nb_sync(NB_ST0, 256);
      contract(kc, stg1, 1);
      TS(6);
      float kv[8];
#pragma unroll
      for (int i = 0; i < 8; i++) kv[i] = w & 2 ? kc[8 + i] : kc[i];
      st_x(pp, nz(pack_bf(kv[0], kv[1])), pack_bf(kv[2], kv[3]), pack_bf(kv[4], kv[5]), pack_bf(kv[6], kv[7]));
      if (c < 2) st_x32(pz, nz(fu(c ? kc[18] : kc[16])));
      TS(5);
    }
    SPLIT();
    WG_WAIT(0);
    packp(p, pw);
#pragma unroll
    for (int u = 0; u < 4; u++) dual_exp(pw + 4 * u, eq + 8 * u);
    SPLIT();
  }
  TS(wg * 16 + 4);
  if (wg == 1) {
    mbar_wait(BAR(MB_UFULL));
    const uint4* ps = g_part + (size_t)hp * 8 * 144 + t;
    const uint32_t* zs = (const uint32_t*)(g_part + (size_t)(hp * 8 + (lane >> 4) * 4) * 144 + 128) + w * 16 + (lane & 15);
    uint4 v[8];
    uint32_t zv[4];
#pragma unroll 1
    for (int it = 0; it < SPIN_MAX; it++) {
#pragma unroll
      for (int i = 0; i < 8; i++) v[i] = ld_x(ps + i * 144);
#pragma unroll
      for (int i = 0; i < 4; i++) zv[i] = ld_x32(zs + i * 576);
      uint32_t m = min(min(zv[0], zv[1]), min(zv[2], zv[3]));
#pragma unroll
      for (int i = 0; i < 8; i++) m = min(m, v[i].x);
      if (__all_sync(0xffffffffu, m != 0)) break;
    }
    float s[8];
    WG_FENCE();
#pragma unroll
    for (int r = 0; r < 8; r++) wgmma_rs_n16(s, v[r], qdesc(sb + OFF_EYE), r);
    WG_COMMIT();
    float zsum = (uf(zv[0]) + uf(zv[1])) + (uf(zv[2]) + uf(zv[3]));
    zsum += __shfl_xor_sync(0xffffffffu, zsum, 16);
    const uint32_t z1 = pack_bf(zsum, 1.f);
    if (lane < 16) sts128(kvs + w * 768 + 512 + lane * 16, z1, z1, z1, z1);
    WG_WAIT(0);
    stsm4(kvs + w * 768 + lane * 16, pack_bf(s[0], s[1]), pack_bf(s[2], s[3]), pack_bf(s[4], s[5]), pack_bf(s[6], s[7]));
    asm volatile("fence.proxy.async.shared::cta;" ::: "memory");
    TS(22);
  }
  nb_sync(NB_KV, 256);
  {
    float n[8][12];
    WG_FENCE();
#pragma unroll
    for (int i = 0; i < 8; i++) wgmma_rs_n24(n[i], make_uint4(eq[4 * i], eq[4 * i + 1], eq[4 * i + 2], eq[4 * i + 3]), qdesc(kvs + (i & 3) * 768), 0);
    WG_COMMIT();
    uint32_t* od = (uint32_t*)(g_o + (size_t)((rt * 4 + wg * 2) * 32 + hp * 2) * 128) + w * 64 + lane;
    WG_WAIT(0);
#pragma unroll
    for (int u = 0; u < 4; u++) {
      float(&np)[12] = n[2 * u];
      const float(&nm)[12] = n[2 * u + 1];
      const float q0 = np[9] * rcp(nm[9]), q1 = np[11] * rcp(nm[11]);
      const float r0 = rcp(fmaf(nm[8], q0, fmaf(np[9], 1e-6f, np[8]))), r1 = rcp(fmaf(nm[10], q1, fmaf(np[11], 1e-6f, np[10])));
#pragma unroll
      for (int i = 0; i < 8; i++) np[i] = fmaf(nm[i], (i & 2) ? q1 : q0, np[i]);
      uint32_t* o = od + (u >> 1) * 16384 + (u & 1) * 512;
      o[0] = pack_bf(np[0] * r0, np[1] * r0);
      o[32] = pack_bf(np[2] * r1, np[3] * r1);
      o[256] = pack_bf(np[4] * r0, np[5] * r0);
      o[288] = pack_bf(np[6] * r1, np[7] * r1);
      if (u == 1) SPLIT();
    }
  }
  TS(wg * 16 + 7);
  nb_arrive(NB_ODONE, 288);
  if (wg) {
    const uint4* src = P.xs + X_Y + (oct * 32 + c * 8) * 256 + (2 * w + (g >> 2)) * 32 + i8 * 4 + (g & 3);
    __nv_bfloat16* dst = P.out + (size_t)((2 * w + (g >> 2)) * 256 + i8 * 16 + (g & 3) * 2) * 1024 + 512 + oct * 32 + c * 8;
    nb_sync(NB_Y + w, 160);
    uint4 v[8];
#pragma unroll 1
    for (int it = 0; it < SPIN_MAX; it++) {
      uint32_t m = 0xffffffffu;
#pragma unroll
      for (int i = 0; i < 8; i++) v[i] = ld_x(src + i * 256);
#pragma unroll
      for (int i = 0; i < 8; i++) m = min(m, v[i].x);
      if (__all_sync(0xffffffffu, m != 0)) break;
    }
#pragma unroll
    for (int i = 0; i < 8; i++) *(uint4*)(dst + (size_t)((i >> 2) * 128 + ((i >> 1) & 1) * 8 + (i & 1)) * 1024) = tr_row(v, i);
    TS(31);
    GT(63);
    if (w == 0) TSDUMP(16);
    return;
  }
  mbar_wait(BAR(MB_WO));
  nb_sync(NB_BDONE, 288);
  TS(8);
  mbar_spin(BAR(MB_OA));
  TS(9);
  float oc[64];
  {
    constexpr uint64_t ha = mkdesc(0, 0, 128, 0), hb = mkdesc(0, 0, 1024, 1);
    constexpr uint32_t da0 = (uint32_t)mkdesc(stg1, 1024, 0, 0), db0 = (uint32_t)mkdesc(sb + OFF_W, 8192, 0, 0);
#pragma unroll 1
    for (int j = 0; j < 8; j++) {
      const int kb = (j + 7) & 7;
      if ((j & 3) == 1) mbar_spin(j == 1 ? BAR(MB_OC) : BAR(MB_OB));
      WG_FENCE();
#pragma unroll
      for (int k = 0; k < 4; k++) wgmma_ss_n128(oc, ha | (da0 + 512 * kb + 128 * k), hb | (db0 + 1024 * kb + 128 * k), k ? 1 : j);
      WG_COMMIT();
    }
    WG_WAIT(0);
  }
  TS(10);
  const uint32_t ot = ((sb + OFF_T + 1023) & ~1023u) + w * 4096;
#pragma unroll
  for (int hf = 0; hf < 2; hf++) {
#pragma unroll
    for (int i = 8 * hf; i < 8 * hf + 8; i += 2)
      stsm4(ot + hf * 2048 + (lane & 15) * 128 + (((i + (lane >> 4)) ^ lane) & 7) * 16, pack_bf(oc[4 * i], oc[4 * i + 1]),
            pack_bf(oc[4 * i + 2], oc[4 * i + 3]), pack_bf(oc[4 * i + 4], oc[4 * i + 5]), pack_bf(oc[4 * i + 6], oc[4 * i + 7]));
    asm volatile("fence.proxy.async.shared::cta;" ::: "memory");
    __syncwarp();
    e_store2d(&mout, ot + hf * 2048, (hp & 3) * 128 + hf * 64, (rt * 4 + (hp >> 2)) * 64 + w * 16);
  }
  asm volatile(ELECT "cp.async.bulk.commit_group;\n@p cp.async.bulk.wait_group.read 0;\n}\n" ::: "memory");
  TS(wg * 16 + 11);
  GT(61 + wg);
  if (w == 0) TSDUMP(0);
  if (w == 1) TSDUMP(48);
}

typedef CUresult (*EncodeFn)(CUtensorMap*, CUtensorMapDataType, cuuint32_t, void*, const cuuint64_t*, const cuuint64_t*,
                             const cuuint32_t*, const cuuint32_t*, CUtensorMapInterleave, CUtensorMapSwizzle,
                             CUtensorMapL2promotion, CUtensorMapFloatOOBfill);

}

extern "C" void kernel_launch(void* const* d_in, const int* in_sizes, int n_in, void* d_out, int out_size) {
  (void)in_sizes; (void)n_in; (void)out_size;
  void* fn = nullptr;
  cudaDriverEntryPointQueryResult qr;
  cudaGetDriverEntryPoint("cuTensorMapEncodeTiled", &fn, cudaEnableDefault, &qr);
  EncodeFn enc = (EncodeFn)fn;
  CUtensorMap mx, mw, mo, mout, mw4;
  const cuuint32_t es[5] = {1, 1, 1, 1, 1};
  {
    cuuint64_t dims[2] = {512, 2048}, st[1] = {1024};
    cuuint32_t box[2] = {64, 128};
    enc(&mx, CU_TENSOR_MAP_DATA_TYPE_BFLOAT16, 2, d_in[0], dims, st, box, es, CU_TENSOR_MAP_INTERLEAVE_NONE,
        CU_TENSOR_MAP_SWIZZLE_128B, CU_TENSOR_MAP_L2_PROMOTION_L2_128B, CU_TENSOR_MAP_FLOAT_OOB_FILL_NONE);
  }
  {
    cuuint64_t dims[3] = {512, 512, 3}, st[2] = {3072, 1024};
    cuuint32_t box[3] = {32, 64, 3};
    enc(&mw, CU_TENSOR_MAP_DATA_TYPE_BFLOAT16, 3, d_in[1], dims, st, box, es, CU_TENSOR_MAP_INTERLEAVE_NONE,
        CU_TENSOR_MAP_SWIZZLE_64B, CU_TENSOR_MAP_L2_PROMOTION_L2_128B, CU_TENSOR_MAP_FLOAT_OOB_FILL_NONE);
  }
  {
    cuuint64_t dims[3] = {64, 512, 8}, st[2] = {1024, 128};
    cuuint32_t box[3] = {64, 64, 2};
    enc(&mo, CU_TENSOR_MAP_DATA_TYPE_BFLOAT16, 3, d_in[3], dims, st, box, es, CU_TENSOR_MAP_INTERLEAVE_NONE,
        CU_TENSOR_MAP_SWIZZLE_128B, CU_TENSOR_MAP_L2_PROMOTION_L2_128B, CU_TENSOR_MAP_FLOAT_OOB_FILL_NONE);
  }
  {
    cuuint64_t dims[2] = {1024, 2048}, st[1] = {2048};
    cuuint32_t box[2] = {64, 16};
    enc(&mout, CU_TENSOR_MAP_DATA_TYPE_BFLOAT16, 2, d_out, dims, st, box, es, CU_TENSOR_MAP_INTERLEAVE_NONE,
        CU_TENSOR_MAP_SWIZZLE_128B, CU_TENSOR_MAP_L2_PROMOTION_NONE, CU_TENSOR_MAP_FLOAT_OOB_FILL_NONE);
  }
  {
    cuuint64_t dims[4] = {512, 64, 3, 8}, st[3] = {3072, 1024, 64 * 3072};
    cuuint32_t box[4] = {32, 64, 3, 2};
    enc(&mw4, CU_TENSOR_MAP_DATA_TYPE_BFLOAT16, 4, d_in[1], dims, st, box, es, CU_TENSOR_MAP_INTERLEAVE_NONE,
        CU_TENSOR_MAP_SWIZZLE_64B, CU_TENSOR_MAP_L2_PROMOTION_L2_128B, CU_TENSOR_MAP_FLOAT_OOB_FILL_NONE);
  }
  Params P;
  P.x = (const __nv_bfloat16*)d_in[0];
  P.u = (const __nv_bfloat16*)d_in[4];
  P.wphi = (const __nv_bfloat16*)d_in[2];
  P.wo = (const __nv_bfloat16*)d_in[3];
  P.logA = (const __nv_bfloat16*)d_in[5];
  P.Aim = (const __nv_bfloat16*)d_in[6];
  P.Cre = (const __nv_bfloat16*)d_in[7];
  P.Cim = (const __nv_bfloat16*)d_in[8];
  P.logdt = (const __nv_bfloat16*)d_in[9];
  P.Dskip = (const __nv_bfloat16*)d_in[10];
  P.out = (__nv_bfloat16*)d_out;
  cudaGetSymbolAddress((void**)&P.xs, g_x);
  P.ts = nullptr;
  cudaFuncSetAttribute(fused_kernel, cudaFuncAttributeMaxDynamicSharedMemorySize, SMEM_BYTES);
  fused_kernel<<<NCTA, NTHREADS, SMEM_BYTES>>>(P, mx, mw, mo, mout, mw4);
}
```

```cpp
#include <cuda_runtime.h>
#include <cuda_bf16.h>
#include <cuda_fp16.h>
#include <cuda.h>
#include <stdint.h>

#define DBG_TS 0

namespace {

constexpr int NTHREADS = 512;
constexpr int NCTA = 128;
constexpr int OFF_W = 0;
constexpr int OFF_X = 98304;
constexpr int OFF_U = OFF_X + 65536;
constexpr int U_CH = 4416, U_ODD = 2240, U_PAD = 128;
constexpr int OFF_STG0 = OFF_U + 18432;
constexpr int SLAB = 3328;
constexpr int OFF_T = OFF_STG0 + 8 * SLAB;
constexpr int T_CH = 5216;
constexpr int T_D = 0;
constexpr int T_5 = 2144;
constexpr int T_3 = T_5 + 384;
constexpr int T_7 = T_5 + 1024;
constexpr int T_9 = T_7 + 320;
constexpr int T_KC = T_9 + 320;
constexpr int T_ST = T_5 - 1024;
constexpr int OFF_PHI = OFF_T + 4 * T_CH;
constexpr int OFF_EYE = OFF_PHI + 1024, OFF_ONE = OFF_EYE + 512;
constexpr int OFF_BAR = OFF_ONE + 256;
constexpr int SMEM_BYTES = OFF_BAR + 512 + 256 * DBG_TS;
constexpr uint32_t SB = 1024;
static_assert(T_KC + 2 * 656 <= T_CH, "table size");
static_assert(SMEM_BYTES <= 232448, "smem");
constexpr int MB_URAW = 0, MB_FULL = 1  , MB_WO = 17, MB_UFULL = 18, MB_OA = 19, MB_OB = 20, MB_OC = 21,
              MB_EMPTY = 22  , MB_AUX = 38;
__host__ __device__ constexpr uint32_t BAR(int i) { return SB + OFF_BAR + 8 * i; }
constexpr int NB_WG0 = 1, NB_ODONE = 2, NB_ST0 = 3  , NB_KV = 5, NB_YZ = 6, NB_INIT = 7, NB_PREP = 8, NB_PROD = 9, NB_KREAD = 10, NB_BDONE = 11, NB_GATE = 12,
              NB_Y = 7  ;
#define X2_AT -1
#define GATE_B 0
#define U_AT 2
#define ZERO_STEP 12
constexpr int SPIN_MAX = 1 << 16;

constexpr int X_CNT = 0;
constexpr int X_PART = 256;
constexpr int X_O = X_PART + 16 * 8 * 144;
constexpr int X_Y = X_O + 32 * 32 * 128;
constexpr int X_UT = X_Y + 512 * 8 * 32;
constexpr int X_SIZE = X_UT + 512 * (U_CH / 16);
__device__ __align__(128) uint4 g_x[X_SIZE];
extern __shared__ uint8_t smem_raw[];
#define TS(i) do {} while (0)
#define TS1(i) do {} while (0)
#define GT(i) do {} while (0)
#define TSDUMP(base) do {} while (0)

__device__ __forceinline__ uint32_t smem_u32(const void* p) { return (uint32_t)__cvta_generic_to_shared(p); }
__device__ __forceinline__ void mbar_arrive(uint32_t b) {
  asm volatile("mbarrier.arrive.shared::cta.b64 _, [%0];" ::"r"(b) : "memory");
}
__device__ __forceinline__ void mbar_wait(uint32_t b) {
  uint32_t done = 0;
#pragma unroll 1
  for (int i = 0; i < SPIN_MAX && !done; i++) {
    asm volatile("{\n.reg .pred p;\nmbarrier.try_wait.parity.shared::cta.b64 p, [%1], 0, 4000;\nselp.u32 %0, 1, 0, p;\n}\n"
                 : "=r"(done) : "r"(b) : "memory");
  }
}
__device__ __forceinline__ void mbar_spin(uint32_t b) {
  uint32_t done = 0;
#pragma unroll 1
  for (int i = 0; i < (SPIN_MAX << 4) && !done; i++) {
    asm volatile("{\n.reg .pred p;\nmbarrier.try_wait.parity.shared::cta.b64 p, [%1], 0;\nselp.u32 %0, 1, 0, p;\n}\n"
                 : "=r"(done) : "r"(b) : "memory");
  }
}
__device__ __forceinline__ void mbar_init(uint32_t b, int n) {
  asm volatile("mbarrier.init.shared::cta.b64 [%0], %1;" ::"r"(b), "r"(n) : "memory");
}
__device__ __forceinline__ void mbar_expect(uint32_t b, int bytes) {
  asm volatile("mbarrier.arrive.expect_tx.shared::cta.b64 _, [%0], %1;" ::"r"(b), "r"(bytes) : "memory");
}
__device__ __forceinline__ void nb_sync(int id, int n) { asm volatile("bar.sync %0, %1;" ::"r"(id), "r"(n) : "memory"); }
__device__ __forceinline__ void nb_arrive(int id, int n) { asm volatile("bar.arrive %0, %1;" ::"r"(id), "r"(n) : "memory"); }
#define ELECT "{\n.reg .pred p;\nelect.sync _|p, 0xffffffff;\n@p "
__device__ __forceinline__ void e_arrive(uint32_t b) {
  asm volatile(ELECT "mbarrier.arrive.shared::cta.b64 _, [%0];\n}\n" ::"r"(b) : "memory");
}
__device__ __forceinline__ void e_expect(uint32_t b, int bytes) {
  asm volatile(ELECT "mbarrier.arrive.expect_tx.shared::cta.b64 _, [%0], %1;\n}\n" ::"r"(b), "r"(bytes) : "memory");
}
__device__ __forceinline__ void e_tma2d(uint32_t dst, const CUtensorMap* m, uint32_t bar, int c0, int c1) {
  asm volatile(ELECT "cp.async.bulk.tensor.2d.shared::cluster.global.mbarrier::complete_tx::bytes [%0], [%1, {%3,%4}], [%2];\n}\n"
               ::"r"(dst), "l"(m), "r"(bar), "r"(c0), "r"(c1) : "memory");
}
__device__ __forceinline__ void e_tma3d(uint32_t dst, const CUtensorMap* m, uint32_t bar, int c0, int c1, int c2) {
  asm volatile(ELECT "cp.async.bulk.tensor.3d.shared::cluster.global.mbarrier::complete_tx::bytes [%0], [%1, {%3,%4,%5}], [%2];\n}\n"
               ::"r"(dst), "l"(m), "r"(bar), "r"(c0), "r"(c1), "r"(c2) : "memory");
}
__device__ __forceinline__ void e_tma4d(uint32_t dst, const CUtensorMap* m, uint32_t bar, int c0, int c3) {
  asm volatile(ELECT "cp.async.bulk.tensor.4d.shared::cluster.global.mbarrier::complete_tx::bytes [%0], [%1, {%3,%5,%5,%4}], [%2];\n}\n"
               ::"r"(dst), "l"(m), "r"(bar), "r"(c0), "r"(c3), "r"(0) : "memory");
}
__device__ __forceinline__ void e_bulk(uint32_t dst, const void* src, int bytes, uint32_t bar) {
  asm volatile(ELECT "cp.async.bulk.shared::cluster.global.mbarrier::complete_tx::bytes [%0], [%1], %2, [%3];\n}\n"
               ::"r"(dst), "l"(src), "r"(bytes), "r"(bar) : "memory");
}
__device__ __forceinline__ void e_prefetch(const void* p, int bytes) {
  asm volatile(ELECT "cp.async.bulk.prefetch.L2.global [%0], %1;\n}\n" ::"l"(p), "r"(bytes) : "memory");
}
__device__ __forceinline__ void e_store2d(const CUtensorMap* m, uint32_t src, int c0, int c1) {
  asm volatile(ELECT "cp.async.bulk.tensor.2d.global.shared::cta.bulk_group [%0, {%2,%3}], [%1];\n}\n"
               ::"l"(m), "r"(src), "r"(c0), "r"(c1) : "memory");
}
__host__ __device__ constexpr uint64_t mkdesc(uint32_t addr, uint32_t lbo, uint32_t sbo, int swz) {
  return (uint64_t)((addr & 0x3FFFF) >> 4) | ((uint64_t)(lbo >> 4) << 16) | ((uint64_t)(sbo >> 4) << 32) |
         ((uint64_t)swz << 62);
}
#define SPLIT() asm volatile("{\n.reg .pred p;\nsetp.eq.u32 p, %0, %1;\n@p exit;\n}\n" ::"r"(blockIdx.y), "n"(__LINE__) : "memory")
#define WG_FENCE() asm volatile("wgmma.fence.sync.aligned;" ::: "memory")
#define WG_COMMIT() asm volatile("wgmma.commit_group.sync.aligned;" ::: "memory")
#define WG_WAIT(n) asm volatile("wgmma.wait_group.sync.aligned " #n ";" ::: "memory")

__device__ __forceinline__ void mma(float& d0, float& d1, float& d2, float& d3, uint32_t a0, uint32_t a1, uint32_t a2,
                                    uint32_t a3, uint32_t b0, uint32_t b1) {
  asm volatile("mma.sync.aligned.m16n8k16.row.col.f32.bf16.bf16.f32 {%0,%1,%2,%3},{%4,%5,%6,%7},{%8,%9},{%0,%1,%2,%3};"
               : "+f"(d0), "+f"(d1), "+f"(d2), "+f"(d3)
               : "r"(a0), "r"(a1), "r"(a2), "r"(a3), "r"(b0), "r"(b1));
}
__device__ __forceinline__ void mmac(float (&d)[4], uint32_t a0, uint32_t a1, uint32_t a2, uint32_t a3, uint32_t b0,
                                     uint32_t b1, const float (&c)[4]) {
  asm volatile("mma.sync.aligned.m16n8k16.row.col.f32.bf16.bf16.f32 {%0,%1,%2,%3},{%4,%5,%6,%7},{%8,%9},{%10,%11,%12,%13};"
               : "=f"(d[0]), "=f"(d[1]), "=f"(d[2]), "=f"(d[3])
               : "r"(a0), "r"(a1), "r"(a2), "r"(a3), "r"(b0), "r"(b1), "f"(c[0]), "f"(c[1]), "f"(c[2]), "f"(c[3]));
}
__device__ __forceinline__ void mma_p(int p, float (&d)[4], uint32_t a0, uint32_t a1, uint32_t a2, uint32_t a3, uint32_t b0, uint32_t b1) {
  asm volatile("{\n.reg .pred q;\nsetp.ne.b32 q, %10, 0;\n"
               "@q mma.sync.aligned.m16n8k16.row.col.f32.bf16.bf16.f32 {%0,%1,%2,%3},{%4,%5,%6,%7},{%8,%9},{%0,%1,%2,%3};\n}\n"
               : "+f"(d[0]), "+f"(d[1]), "+f"(d[2]), "+f"(d[3])
               : "r"(a0), "r"(a1), "r"(a2), "r"(a3), "r"(b0), "r"(b1), "r"(p));
}
__device__ __forceinline__ void mmac_p(int p, float (&d)[4], uint32_t a0, uint32_t a1, uint32_t a2, uint32_t a3, uint32_t b0,
                                       uint32_t b1, const float (&c)[4]) {
  asm volatile("{\n.reg .pred q;\nsetp.ne.b32 q, %14, 0;\n"
               "@q mma.sync.aligned.m16n8k16.row.col.f32.bf16.bf16.f32 {%0,%1,%2,%3},{%4,%5,%6,%7},{%8,%9},{%10,%11,%12,%13};\n}\n"
               : "+f"(d[0]), "+f"(d[1]), "+f"(d[2]), "+f"(d[3])
               : "r"(a0), "r"(a1), "r"(a2), "r"(a3), "r"(b0), "r"(b1), "f"(c[0]), "f"(c[1]), "f"(c[2]), "f"(c[3]), "r"(p));
}
__device__ __forceinline__ void mma_h(float (&d)[4], const uint32_t (&a)[4], uint32_t b0, uint32_t b1) {
  asm volatile("mma.sync.aligned.m16n8k16.row.col.f32.f16.f16.f32 {%0,%1,%2,%3},{%4,%5,%6,%7},{%8,%9},{%0,%1,%2,%3};"
               : "+f"(d[0]), "+f"(d[1]), "+f"(d[2]), "+f"(d[3]) : "r"(a[0]), "r"(a[1]), "r"(a[2]), "r"(a[3]), "r"(b0), "r"(b1));
}
__device__ __forceinline__ void mma0(float& d0, float& d1, float& d2, float& d3, uint32_t a0, uint32_t a1, uint32_t a2,
                                     uint32_t a3, uint32_t b0, uint32_t b1) {
  asm volatile("mma.sync.aligned.m16n8k16.row.col.f32.bf16.bf16.f32 {%0,%1,%2,%3},{%4,%5,%6,%7},{%8,%9},{%10,%10,%10,%10};"
               : "=f"(d0), "=f"(d1), "=f"(d2), "=f"(d3)
               : "r"(a0), "r"(a1), "r"(a2), "r"(a3), "r"(b0), "r"(b1), "f"(0.f));
}
__device__ __forceinline__ uint32_t pack_bf(float lo, float hi) {
  uint32_t r;
  asm("cvt.rn.bf16x2.f32 %0, %1, %2;" : "=r"(r) : "f"(hi), "f"(lo));
  return r;
}
__device__ __forceinline__ float bf_lo(uint32_t w) { return __uint_as_float(w << 16); }
__device__ __forceinline__ float bf_hi(uint32_t w) { return __uint_as_float(w & 0xffff0000u); }
__device__ __forceinline__ float bf_round(float x) { return __bfloat162float(__float2bfloat16_rn(x)); }
__device__ __forceinline__ uint32_t bmax2(uint32_t a, uint32_t b) {
  uint32_t r; asm("max.bf16x2 %0, %1, %2;" : "=r"(r) : "r"(a), "r"(b)); return r;
}
__device__ __forceinline__ uint32_t bmin2(uint32_t a, uint32_t b) {
  uint32_t r; asm("min.bf16x2 %0, %1, %2;" : "=r"(r) : "r"(a), "r"(b)); return r;
}
__device__ __forceinline__ float ex2(float x) { float r; asm("ex2.approx.ftz.f32 %0, %1;" : "=f"(r) : "f"(x)); return r; }
__device__ __forceinline__ float rcp(float x) { float r; asm("rcp.approx.ftz.f32 %0, %1;" : "=f"(r) : "f"(x)); return r; }
__device__ __forceinline__ void ldsm4(uint32_t (&r)[4], uint32_t a) {
  asm volatile("ldmatrix.sync.aligned.m8n8.x4.shared.b16 {%0,%1,%2,%3}, [%4];"
               : "=r"(r[0]), "=r"(r[1]), "=r"(r[2]), "=r"(r[3]) : "r"(a) : "memory");
}
__device__ __forceinline__ void ldsm4t(uint32_t (&r)[4], uint32_t a) {
  asm volatile("ldmatrix.sync.aligned.m8n8.x4.trans.shared.b16 {%0,%1,%2,%3}, [%4];"
               : "=r"(r[0]), "=r"(r[1]), "=r"(r[2]), "=r"(r[3]) : "r"(a) : "memory");
}
__device__ __forceinline__ void stsm4(uint32_t a, uint32_t r0, uint32_t r1, uint32_t r2, uint32_t r3) {
  asm volatile("stmatrix.sync.aligned.m8n8.x4.shared.b16 [%0], {%1,%2,%3,%4};"
               ::"r"(a), "r"(r0), "r"(r1), "r"(r2), "r"(r3) : "memory");
}
__device__ __forceinline__ uint32_t lds32(uint32_t a) {
  uint32_t r; asm volatile("ld.shared.u32 %0, [%1];" : "=r"(r) : "r"(a) : "memory"); return r;
}
__device__ __forceinline__ uint32_t lds16(uint32_t a) {
  uint32_t r; asm volatile("{\n.reg .u16 h;\nld.shared.u16 h, [%1];\ncvt.u32.u16 %0, h;\n}\n" : "=r"(r) : "r"(a) : "memory"); return r;
}
__device__ __forceinline__ uint2 lds64(uint32_t a) {
  uint2 r; asm volatile("ld.shared.v2.u32 {%0,%1}, [%2];" : "=r"(r.x), "=r"(r.y) : "r"(a) : "memory"); return r;
}
__device__ __forceinline__ uint4 lds128(uint32_t a) {
  uint4 r;
  asm volatile("ld.shared.v4.u32 {%0,%1,%2,%3}, [%4];" : "=r"(r.x), "=r"(r.y), "=r"(r.z), "=r"(r.w) : "r"(a) : "memory");
  return r;
}
__device__ __forceinline__ void sts32(uint32_t a, uint32_t v) { asm volatile("st.shared.u32 [%0], %1;" ::"r"(a), "r"(v) : "memory"); }
__device__ __forceinline__ void sts16(uint32_t a, uint32_t v) {
  asm volatile("{\n.reg .u16 h;\ncvt.u16.u32 h, %1;\nst.shared.u16 [%0], h;\n}\n" ::"r"(a), "r"(v) : "memory");
}
__device__ __forceinline__ void sts64(uint32_t a, uint32_t x, uint32_t y) {
  asm volatile("st.shared.v2.u32 [%0], {%1,%2};" ::"r"(a), "r"(x), "r"(y) : "memory");
}
__device__ __forceinline__ void sts128(uint32_t a, uint32_t x, uint32_t y, uint32_t z, uint32_t w) {
  asm volatile("st.shared.v4.u32 [%0], {%1,%2,%3,%4};" ::"r"(a), "r"(x), "r"(y), "r"(z), "r"(w) : "memory");
}
__device__ __forceinline__ uint4 ld_x(const uint4* p) {
  uint4 r;
  asm volatile("{\n.reg .b128 t;\nld.relaxed.gpu.global.b128 t, [%4];\nmov.b128 {%0,%1,%2,%3}, t;\n}\n"
               : "=r"(r.x), "=r"(r.y), "=r"(r.z), "=r"(r.w) : "l"(p) : "memory");
  return r;
}
__device__ __forceinline__ uint32_t ld_x32(const uint32_t* p) {
  uint32_t r; asm volatile("ld.relaxed.gpu.global.u32 %0, [%1];" : "=r"(r) : "l"(p) : "memory"); return r;
}
__device__ __forceinline__ void st_x(uint4* p, uint32_t x, uint32_t y, uint32_t z, uint32_t w) {
  asm volatile("{\n.reg .b128 t;\nmov.b128 t, {%1,%2,%3,%4};\nst.relaxed.gpu.global.b128 [%0], t;\n}\n"
               ::"l"(p), "r"(x), "r"(y), "r"(z), "r"(w) : "memory");
}
__device__ __forceinline__ void st_x_p(int p, uint4* a, uint32_t x, uint32_t y, uint32_t z, uint32_t w) {
  asm volatile("{\n.reg .b128 t;\n.reg .pred q;\nsetp.ne.b32 q, %5, 0;\nmov.b128 t, {%1,%2,%3,%4};\n@q st.relaxed.gpu.global.b128 [%0], t;\n}\n"
               ::"l"(a), "r"(x), "r"(y), "r"(z), "r"(w), "r"(p) : "memory");
}
__device__ __forceinline__ void sts64_p(int p, uint32_t a, uint32_t x, uint32_t y) {
  asm volatile("{\n.reg .pred q;\nsetp.ne.b32 q, %3, 0;\n@q st.shared.v2.u32 [%0], {%1,%2};\n}\n" ::"r"(a), "r"(x), "r"(y), "r"(p) : "memory");
}
__device__ __forceinline__ void st_x32(uint32_t* p, uint32_t x) {
  asm volatile("st.relaxed.gpu.global.u32 [%0], %1;" ::"l"(p), "r"(x) : "memory");
}
__device__ __forceinline__ uint32_t nz(uint32_t w) { return max(w, 1u); }
__device__ __forceinline__ uint32_t fu(float x) { return __float_as_uint(x); }
__device__ __forceinline__ float uf(uint32_t x) { return __uint_as_float(x); }

__device__ __forceinline__ void wgmma_ss_n96(float (&d)[48], uint64_t da, uint64_t db, int sc) {
  asm volatile("{\n.reg .pred p;\nsetp.ne.b32 p, %50, 0;\n"
      "wgmma.mma_async.sync.aligned.m64n96k16.f32.bf16.bf16 "
      "{%0,%1,%2,%3,%4,%5,%6,%7,%8,%9,%10,%11,%12,%13,%14,%15,%16,%17,%18,%19,%20,%21,%22,%23,%24,%25,%26,%27,%28,%29,%30,%31,%32,%33,%34,%35,%36,%37,%38,%39,%40,%41,%42,%43,%44,%45,%46,%47}, "
      "%48, %49, p, 1, 1, 0, 1;\n}\n"
      : "+f"(d[0]), "+f"(d[1]), "+f"(d[2]), "+f"(d[3]), "+f"(d[4]), "+f"(d[5]), "+f"(d[6]), "+f"(d[7]),
        "+f"(d[8]), "+f"(d[9]), "+f"(d[10]), "+f"(d[11]), "+f"(d[12]), "+f"(d[13]), "+f"(d[14]), "+f"(d[15]),
        "+f"(d[16]), "+f"(d[17]), "+f"(d[18]), "+f"(d[19]), "+f"(d[20]), "+f"(d[21]), "+f"(d[22]), "+f"(d[23]),
        "+f"(d[24]), "+f"(d[25]), "+f"(d[26]), "+f"(d[27]), "+f"(d[28]), "+f"(d[29]), "+f"(d[30]), "+f"(d[31]),
        "+f"(d[32]), "+f"(d[33]), "+f"(d[34]), "+f"(d[35]), "+f"(d[36]), "+f"(d[37]), "+f"(d[38]), "+f"(d[39]),
        "+f"(d[40]), "+f"(d[41]), "+f"(d[42]), "+f"(d[43]), "+f"(d[44]), "+f"(d[45]), "+f"(d[46]), "+f"(d[47])
      : "l"(da), "l"(db), "r"(sc));
}

__device__ __forceinline__ void wgmma_ss_n128(float (&d)[64], uint64_t da, uint64_t db, int sc) {
  asm volatile("{\n.reg .pred p;\nsetp.ne.b32 p, %66, 0;\n"
      "wgmma.mma_async.sync.aligned.m64n128k16.f32.bf16.bf16 "
      "{%0,%1,%2,%3,%4,%5,%6,%7,%8,%9,%10,%11,%12,%13,%14,%15,%16,%17,%18,%19,%20,%21,%22,%23,%24,%25,%26,%27,%28,%29,%30,%31,%32,%33,%34,%35,%36,%37,%38,%39,%40,%41,%42,%43,%44,%45,%46,%47,%48,%49,%50,%51,%52,%53,%54,%55,%56,%57,%58,%59,%60,%61,%62,%63}, "
      "%64, %65, p, 1, 1, 0, 1;\n}\n"
      : "+f"(d[0]), "+f"(d[1]), "+f"(d[2]), "+f"(d[3]), "+f"(d[4]), "+f"(d[5]), "+f"(d[6]), "+f"(d[7]),
        "+f"(d[8]), "+f"(d[9]), "+f"(d[10]), "+f"(d[11]), "+f"(d[12]), "+f"(d[13]), "+f"(d[14]), "+f"(d[15]),
        "+f"(d[16]), "+f"(d[17]), "+f"(d[18]), "+f"(d[19]), "+f"(d[20]), "+f"(d[21]), "+f"(d[22]), "+f"(d[23]),
        "+f"(d[24]), "+f"(d[25]), "+f"(d[26]), "+f"(d[27]), "+f"(d[28]), "+f"(d[29]), "+f"(d[30]), "+f"(d[31]),
        "+f"(d[32]), "+f"(d[33]), "+f"(d[34]), "+f"(d[35]), "+f"(d[36]), "+f"(d[37]), "+f"(d[38]), "+f"(d[39]),
        "+f"(d[40]), "+f"(d[41]), "+f"(d[42]), "+f"(d[43]), "+f"(d[44]), "+f"(d[45]), "+f"(d[46]), "+f"(d[47]),
        "+f"(d[48]), "+f"(d[49]), "+f"(d[50]), "+f"(d[51]), "+f"(d[52]), "+f"(d[53]), "+f"(d[54]), "+f"(d[55]),
        "+f"(d[56]), "+f"(d[57]), "+f"(d[58]), "+f"(d[59]), "+f"(d[60]), "+f"(d[61]), "+f"(d[62]), "+f"(d[63])
      : "l"(da), "l"(db), "r"(sc));
}

__device__ __forceinline__ void wgmma_ss_n40(float (&d)[20], uint64_t da, uint64_t db, int sc) {
  asm volatile("{\n.reg .pred p;\nsetp.ne.b32 p, %22, 0;\n"
      "wgmma.mma_async.sync.aligned.m64n40k16.f32.bf16.bf16 "
      "{%0,%1,%2,%3,%4,%5,%6,%7,%8,%9,%10,%11,%12,%13,%14,%15,%16,%17,%18,%19}, "
      "%20, %21, p, 1, 1, 1, 1;\n}\n"
      : "+f"(d[0]), "+f"(d[1]), "+f"(d[2]), "+f"(d[3]), "+f"(d[4]), "+f"(d[5]), "+f"(d[6]), "+f"(d[7]),
        "+f"(d[8]), "+f"(d[9]), "+f"(d[10]), "+f"(d[11]), "+f"(d[12]), "+f"(d[13]), "+f"(d[14]), "+f"(d[15]),
        "+f"(d[16]), "+f"(d[17]), "+f"(d[18]), "+f"(d[19])
      : "l"(da), "l"(db), "r"(sc));
}

__device__ __forceinline__ void wgmma_rs_n8(float (&d)[4], const uint4& a, uint64_t db, int sc) {
  asm volatile("{\n.reg .pred p;\nsetp.ne.b32 p, %9, 0;\n"
      "wgmma.mma_async.sync.aligned.m64n8k16.f32.bf16.bf16 "
      "{%0,%1,%2,%3}, "
      "{%4,%5,%6,%7}, %8, p, 1, 1, 1;\n}\n"
      : "+f"(d[0]), "+f"(d[1]), "+f"(d[2]), "+f"(d[3])
      : "r"(a.x), "r"(a.y), "r"(a.z), "r"(a.w), "l"(db), "r"(sc));
}

__device__ __forceinline__ void wgmma_rs_n16(float (&d)[8], const uint4& a, uint64_t db, int sc) {
  asm volatile("{\n.reg .pred p;\nsetp.ne.b32 p, %13, 0;\n"
      "wgmma.mma_async.sync.aligned.m64n16k16.f32.bf16.bf16 "
      "{%0,%1,%2,%3,%4,%5,%6,%7}, "
      "{%8,%9,%10,%11}, %12, p, 1, 1, 1;\n}\n"
      : "+f"(d[0]), "+f"(d[1]), "+f"(d[2]), "+f"(d[3]), "+f"(d[4]), "+f"(d[5]), "+f"(d[6]), "+f"(d[7])
      : "r"(a.x), "r"(a.y), "r"(a.z), "r"(a.w), "l"(db), "r"(sc));
}

__device__ __forceinline__ void wgmma_rs_n24(float (&d)[12], const uint4& a, uint64_t db, int sc) {
  asm volatile("{\n.reg .pred p;\nsetp.ne.b32 p, %17, 0;\n"
      "wgmma.mma_async.sync.aligned.m64n24k16.f32.bf16.bf16 "
      "{%0,%1,%2,%3,%4,%5,%6,%7,%8,%9,%10,%11}, "
      "{%12,%13,%14,%15}, %16, p, 1, 1, 1;\n}\n"
      : "+f"(d[0]), "+f"(d[1]), "+f"(d[2]), "+f"(d[3]), "+f"(d[4]), "+f"(d[5]), "+f"(d[6]), "+f"(d[7]),
        "+f"(d[8]), "+f"(d[9]), "+f"(d[10]), "+f"(d[11])
      : "r"(a.x), "r"(a.y), "r"(a.z), "r"(a.w), "l"(db), "r"(sc));
}

struct Params {
  const __nv_bfloat16 *logA, *Aim, *Cre, *Cim, *logdt, *Dskip, *x, *wphi, *wo;
  __nv_bfloat16* out;
  uint4* xs;
  long long* ts;
};

__device__ __forceinline__ uint4 tr_row(const uint4 (&v)[8], int i) {
  uint32_t o[4];
#pragma unroll
  for (int m = 0; m < 4; m++) {
    const uint4 &ra = v[2 * m], &rb = v[2 * m + 1];
    const int k = i >> 1;
    const uint32_t xa = k == 0 ? ra.x : k == 1 ? ra.y : k == 2 ? ra.z : ra.w;
    const uint32_t xb = k == 0 ? rb.x : k == 1 ? rb.y : k == 2 ? rb.z : rb.w;
    o[m] = __byte_perm(xa, xb, (i & 1) ? 0x7632 : 0x5410);
  }
  return make_uint4(o[0], o[1], o[2], o[3]);
}

struct cpx { float r, i; };
__device__ __forceinline__ cpx csq(cpx a) { return {a.r * a.r - a.i * a.i, 2.f * (a.r * a.i)}; }
__device__ __forceinline__ cpx polar(float e, float t) {
  const float m = ex2(e);
  return {m * __cosf(t), m * __sinf(t)};
}

struct KgenRaw { unsigned short la, ai, cr, ci, ldt; };
__device__ __forceinline__ KgenRaw kgen_load(const Params& P, int d, int unit, int lane) {
  const int o = d * 128 + unit * 32 + lane;
  return {__ldg((const unsigned short*)P.logA + o), __ldg((const unsigned short*)P.Aim + o), __ldg((const unsigned short*)P.Cre + o),
          __ldg((const unsigned short*)P.Cim + o), __ldg((const unsigned short*)P.logdt + d)};
}
struct hmul { __half2 a, b; };
__device__ __forceinline__ hmul mk_mul(cpx w) {
  uint32_t b;
  asm("{\n.reg .f32 n;\nneg.ftz.f32 n, %1;\ncvt.rn.f16x2.f32 %0, %2, n;\n}\n" : "=r"(b) : "f"(w.i), "f"(w.r));
  return {__floats2half2_rn(w.r, w.i), *(const __half2*)&b};
}
__device__ __forceinline__ __half2 hcm(__half2 z, const hmul& w) { return __hfma2(__high2half2(z), w.b, __hmul2(__low2half2(z), w.a)); }
__device__ __forceinline__ uint32_t hu(__half2 v) { return *(const uint32_t*)&v; }

struct KgenAddr { uint32_t sa, sb, lb, lc; };
__device__ __forceinline__ KgenAddr kgen_addr(int lane, uint32_t buf) {
  KgenAddr a;
  a.sa = buf + (lane & 7) * 128 + ((((lane >> 3) ^ lane) & 7) << 4);
  a.lb = buf + (lane >> 3) * 128 + (((lane ^ (lane >> 3)) & 7) << 4);
  a.sb = a.sa ^ 64; a.lc = a.lb ^ 64;
  asm volatile("" : "+r"(a.sa), "+r"(a.sb), "+r"(a.lb), "+r"(a.lc));
  return a;
}
__device__ __forceinline__ void kgen_unit(const KgenRaw& r, const KgenAddr& ad, uint32_t zero, float (&k)[5][4], float& k2048, float& sc) {
  const float dt = bf_round(expf(bf_lo(r.ldt)));
  const float a2 = bf_round(ex2(bf_lo(r.la) * 1.4426950408889634f)) * (dt * -1.4426950408889634f);
  const float f = bf_lo(r.ai) * dt;
  const float r128 = f * 20.371832715762604f;
  const uint32_t ex = min(max(__reduce_max_sync(0xffffffffu, max(r.cr & 0x7fffu, r.ci & 0x7fffu)) >> 7, 1u), 253u);
  const float cs = uf((254u - ex) << 23);
  sc = 2.f * dt * uf(ex << 23);
  const cpx C = {bf_lo(r.cr) * cs, -bf_lo(r.ci) * cs};
  uint32_t A[4][4], B[7][2][4];
  auto bounce = [&](const __half2 (&v)[8], int j) {
    stsm4(ad.sa, hu(v[0]), hu(v[1]), hu(v[2]), hu(v[3]));
    stsm4(ad.sb, hu(v[4]), hu(v[5]), hu(v[6]), hu(v[7]));
    __syncwarp();
    ldsm4(B[j][0], ad.lb);
    ldsm4(B[j][1], ad.lc + 512);
  };
  auto tile = [&](int j) {
    k[j][0] = k[j][1] = k[j][2] = k[j][3] = 0.f;
#pragma unroll
    for (int s = 0; s < 4; s++) mma_h(k[j], A[s], B[j][s >> 1][2 * (s & 1)], B[j][s >> 1][2 * (s & 1) + 1]);
  };
  auto after = [&](cpx v, uint32_t dep) { return cpx{uf(fu(v.r) ^ (dep & zero)), v.i}; };
  const cpx w1 = polar(a2, f), w128 = polar(a2 * 128.f, (r128 - rintf(r128)) * 6.283185307179586f);
  const cpx w2 = csq(w1), w4 = csq(w2);
  __half2 t0[8], t1[8], t2[8], t3[8], t4[8];
  const hmul m2 = mk_mul(w2), m4 = mk_mul(w4), m128 = mk_mul(w128);
  t0[0] = __floats2half2_rn(1.f, 0.f); t0[1] = __floats2half2_rn(w1.r, w1.i); t0[2] = m2.a; t0[4] = m4.a;
  t0[3] = hcm(t0[1], m2); t0[5] = hcm(t0[1], m4); t0[6] = hcm(t0[2], m4); t0[7] = hcm(t0[3], m4);
  bounce(t0, 0);
  t1[0] = m128.a;
#pragma unroll
  for (int i = 1; i < 8; i++) t1[i] = hcm(t0[i], m128);
  bounce(t1, 1);
  {
    cpx w8 = csq(after(w4, B[0][0][0]));
    w8.i = -w8.i;
    const cpx w16 = csq(w8), w32 = csq(w16), w64 = csq(w32);
    const hmul m8 = mk_mul(w8), m16 = mk_mul(w16), m32 = mk_mul(w32), m64 = mk_mul(w64);
    __half2 a[8];
    a[0] = __floats2half2_rn(C.r, C.i); a[1] = hcm(a[0], m8);
    a[2] = hcm(a[0], m16); a[3] = hcm(a[1], m16);
#pragma unroll
    for (int i = 0; i < 4; i++) a[4 + i] = hcm(a[i], m32);
    bounce(a, 5);
#pragma unroll
    for (int i = 0; i < 8; i++) a[i] = hcm(a[i], m64);
    bounce(a, 6);
#pragma unroll
    for (int i = 0; i < 16; i++) A[i >> 2][i & 3] = B[5 + (i & 1)][i >> 3][(i >> 1) & 3];
  }
  const cpx w256 = csq(after(w128, B[1][0][0]));
  const hmul m256 = mk_mul(w256);
  t2[0] = m256.a;
#pragma unroll
  for (int i = 1; i < 8; i++) t2[i] = hcm((i & 1) ? t1[i & 6] : t0[i & 6], m256);
  bounce(t2, 2);
  tile(0); tile(1);
  const cpx w512 = csq(after(w256, A[0][0]));
  const hmul m512 = mk_mul(w512);
  t3[0] = m512.a;
#pragma unroll
  for (int i = 1; i < 8; i++) t3[i] = hcm((i & 2) ? t2[i & 5] : ((i & 1) ? t1[i & 4] : t0[i & 4]), m512);
  bounce(t3, 3);
  tile(2);
  const cpx w1024 = csq(after(w512, B[2][0][0])), we = csq(w1024);
  const hmul m1024 = mk_mul(w1024);
  t4[0] = m1024.a;
#pragma unroll
  for (int i = 1; i < 8; i++) t4[i] = hcm((i & 4) ? t3[i & 3] : ((i & 2) ? t2[i & 1] : t1[0]), m1024);
  bounce(t4, 4);
  tile(3); tile(4);
  k2048 = (C.r * we.r + C.i * we.i) * sc;
}

__device__ __forceinline__ void build_tables(uint32_t tb, int lane, float (&k)[5][4], float k2048) {
  const int g = lane >> 2, c = lane & 3;
  const uint32_t kc = tb + T_KC + 16;
  {
    const uint32_t a0 = kc + 16 * g + 4 * c, a2 = kc + 2 * (256 + 4 * g + c);
    const uint32_t a3 = kc + 2 * (384 + 2 * g + 64 * (c & 1) + (c >> 1)), a4 = kc + 2 * (512 + g + 32 * c);
#pragma unroll
    for (int r = 0; r < 2; r++) {
      sts32(a0 + 128 * r, pack_bf(k[0][2 * r], k[0][2 * r + 1]));
      sts32(a0 + 128 * r + 256, pack_bf(k[1][2 * r], k[1][2 * r + 1]));
      const uint32_t w2 = pack_bf(k[2][2 * r], k[2][2 * r + 1]);
      const uint32_t w3 = pack_bf(k[3][2 * r], k[3][2 * r + 1]);
      const uint32_t w4 = pack_bf(k[4][2 * r], k[4][2 * r + 1]);
      sts16(a2 + 64 * r, w2); sts16(a2 + 64 * r + 128, w2 >> 16);
      sts16(a3 + 32 * r, w3); sts16(a3 + 32 * r + 64, w3 >> 16);
      sts16(a4 + 16 * r, w4); sts16(a4 + 16 * r + 32, w4 >> 16);
    }
  }
  if (lane == 0) { sts16(kc + 2 * 640, pack_bf(k2048, 0.f)); sts32(kc - 4, 0); }
  __syncwarp();
  const uint32_t td = tb + T_D + 32;
#pragma unroll
  for (int hf = 0; hf < 2; hf++) {
    const uint2 v = lds64(kc + 256 * hf + 8 * lane);
    const uint32_t pv = lds32(kc + 256 * hf + 8 * lane - 4);
    sts128(td + 512 * hf + 16 * lane, __byte_perm(v.x, pv, 0x7610), __byte_perm(v.x, v.x, 0x1032), __byte_perm(v.y, v.x, 0x7610),
           __byte_perm(v.y, v.y, 0x1032));
  }
#pragma unroll
  for (int hf = 0; hf < 2; hf++) {
    const uint32_t v = lds32(kc + 512 + 128 * hf + 4 * lane), nx = lds32(kc + 516 + 128 * hf + 4 * lane);
    uint32_t w0 = __byte_perm(v, v, 0x1010);
    const uint32_t w1 = w0;
    if (hf == 0) { const uint32_t pv = lds32(kc + 508); if (lane == 0) w0 = __byte_perm(v, pv, 0x7610); }
    sts128(td + 1024 + 512 * hf + 16 * lane, w0, w1, __byte_perm(v, v, 0x1032), __byte_perm(nx, v, 0x7610));
  }
  {
    const uint32_t kk = lds16(kc + 2 * 384);
    const uint32_t w = lane < 3 ? (kk | (kk << 16)) : (lane == 3 ? (kk << 16) : 0u);
    if (lane < 24) sts32(td + 4 * (lane < 16 ? 512 + lane : lane - 24), w);
    const uint32_t lo_ = lds16(kc + 2 * 511), le_ = lds16(kc + 2 * 512);
    const uint32_t ja = tb + T_5 + (lane < 16 ? 4 * lane : 256 + 4 * lane);
    sts32(ja, lane == 16 ? (le_ << 16) : 0u);
    sts32(ja + 384, lane == 16 ? (lo_ << 16) : 0u);
    sts32(tb + (lane < 16 ? T_7 : T_9 - 64) + 4 * lane, 0u);
  }
#pragma unroll
  for (int s = 0; s < 2; s++) {
    const uint32_t b = kc + 2 * (s ? 512 : 384) + 8 * lane;
    const uint2 v = lds64(b);
    uint32_t em = lds16(b - 2), e0 = v.x;
    const uint32_t e4 = lds16(b + 8);
    if (lane == 0) { em = 0; e0 = 0; }
    sts64(tb + (s ? T_7 : T_3) + 64 + 8 * lane, __byte_perm(v.x, em, 0x5432), __byte_perm(v.y, v.x, 0x7632));
    sts64(tb + (s ? T_9 : T_5) + 64 + 8 * lane, __byte_perm(v.y, e0, 0x5410), __byte_perm(e4, v.y, 0x5410));
  }
  __syncwarp();
}

__device__ __forceinline__ uint32_t box2w(int lo, int n, int o) {
  return ((unsigned)(o - lo) < (unsigned)n ? 0x3F80u : 0u) | ((unsigned)(o + 1 - lo) < (unsigned)n ? 0x3F800000u : 0u);
}

__device__ __forceinline__ void conv_channel(uint32_t ub, uint32_t tb, int lane, uint4* ydst) {
  const int g = lane >> 2, c = lane & 3, x = g - 2 * c;
  const int mi = lane >> 3;
  const uint32_t qa = ub + U_PAD + 16 * (lane & 7) + ((mi == 0 || mi == 3) ? U_ODD : 0) - (mi == 0 ? 16 : 0);
  const uint32_t hb = ub + U_PAD + (mi & 1) * U_ODD + 16 * ((lane >> 4) + (lane & 7)) - 16;
  const uint32_t kv = lds16(tb + T_KC + 16 + 2 * 512);
  const int oh = c < 2 ? 8 + 2 * c : 2 * c - 8, og = c < 3 ? 2 * c : -10;
  uint32_t bx[4] = {box2w(g - 4, 9, 2 * c), box2w(g - 3, 7, 2 * c), box2w(g - 4, 9, oh), box2w(g - 3, 7, oh)};
  uint32_t by[4] = {box2w(g - 10, 5, 2 * c - 8), box2w(g - 5, 3, 2 * c - 8), box2w(g - 10, 5, og), box2w(g - 5, 3, og)};
  uint32_t lb0 = ((unsigned)(x + 5) < 2u ? kv : 0u) | ((unsigned)(x + 4) < 2u ? kv << 16 : 0u);
  uint32_t lb1 = ((unsigned)(x - 3) < 2u ? kv : 0u) | ((unsigned)(x - 4) < 2u ? kv << 16 : 0u);
  const int q0 = g - 1, q1 = c < 3 ? g : g - 2;
  uint32_t y0a = ub + U_PAD + (q0 & 1) * U_ODD + 16 * (q0 >> 1) + 4 * c;
  uint32_t y1a = ub + U_PAD + (q1 & 1) * U_ODD + 16 * (q1 >> 1) + 4 * c;
#pragma unroll
  for (int i = 0; i < 4; i++) asm volatile("" : "+r"(bx[i]), "+r"(by[i]));
  asm volatile("" : "+r"(lb0), "+r"(lb1), "+r"(y0a), "+r"(y1a));
  mbar_wait(BAR(MB_UFULL));
  mbar_spin(BAR(MB_EMPTY + 15));
  TS(36);
  float acc[16][4];
  {
    uint32_t z09[8], z07[8], zm9[8], zm7[8];
#pragma unroll
    for (int i = 0; i < 8; i++) {
      uint32_t h[4];
      ldsm4(h, hb + 128 * i);
      float y0, y1, y2, y3, w0, w1, w2, w3;
      mma0(y0, y1, y2, y3, bx[0], bx[1], bx[2], bx[3], h[2], c < 2 ? h[3] : h[1]);
      mma0(w0, w1, w2, w3, bx[0], bx[1], bx[2], bx[3], h[1], c < 2 ? h[2] : h[0]);
      z09[i] = pack_bf(y0, y1); z07[i] = pack_bf(y2, y3);
      zm9[i] = pack_bf(w0, w1); zm7[i] = pack_bf(w2, w3);
    }
  uint32_t f3[3][4][4];
  {
    const uint32_t fa = tb + T_7 + 4 * (16 + x);
#pragma unroll
    for (int tt = 0; tt < 3; tt++)
#pragma unroll
      for (int D = 0; D < 4; D++) {
        const uint32_t a = fa + (tt == 0 ? 316 : (tt == 1 ? 320 : 0)) + 64 * D;
        f3[tt][D][0] = lds32(a); f3[tt][D][1] = lds32(a + 32); f3[tt][D][2] = lds32(a - 32); f3[tt][D][3] = lds32(a);
      }
  }
    float a[4][2][4];
#pragma unroll
    for (int kap = 0; kap < 4; kap++)
#pragma unroll
      for (int sg = 0; sg < 2; sg++)
#pragma unroll
        for (int bk = 3; bk >= kap; bk--) {
          const uint32_t(&q0_)[4] = f3[sg ? 2 : 0][bk - kap];
          const uint32_t(&q1_)[4] = f3[sg ? 2 : 1][bk - kap];
          float(&a0)[4] = a[bk][0];
          float(&a1)[4] = a[bk][1];
          if (sg == 0 && kap == 0) {
            mma0(a0[0], a0[1], a0[2], a0[3], q0_[0], q0_[1], q0_[2], q0_[3], z09[0], z09[1]);
            mma0(a1[0], a1[1], a1[2], a1[3], q1_[0], q1_[1], q1_[2], q1_[3], zm9[0], zm9[1]);
          } else {
            mma(a0[0], a0[1], a0[2], a0[3], q0_[0], q0_[1], q0_[2], q0_[3], sg ? zm7[2 * kap] : z09[2 * kap], sg ? zm7[2 * kap + 1] : z09[2 * kap + 1]);
            mma(a1[0], a1[1], a1[2], a1[3], q1_[0], q1_[1], q1_[2], q1_[3], sg ? z07[2 * kap] : zm9[2 * kap], sg ? z07[2 * kap + 1] : zm9[2 * kap + 1]);
          }
        }
    SPLIT();
#pragma unroll
    for (int i = 0; i < 8; i++) {
      uint32_t h[4];
      ldsm4(h, qa + 128 * i);
      const float ci[4] = {a[i >> 1][0][2 * (i & 1)], a[i >> 1][0][2 * (i & 1) + 1], a[i >> 1][1][2 * (i & 1)], a[i >> 1][1][2 * (i & 1) + 1]};
      mmac(acc[8 + i], h[0], h[1], h[2], h[3], lb0, lb1, ci);
    }
  }
  TS(44);
  {
    uint2 a5[10], a3[10];
    const uint32_t aa = tb + T_5 + 4 * (8 + 2 * g - 2 * c);
#pragma unroll
    for (int m = 0; m < 10; m++) { a5[m] = lds64(aa + 32 * m); a3[m] = lds64(aa + 384 + 32 * m); }
    uint32_t x5[12][2], x3[12][2];
    auto ygen = [&](int kap) {
#pragma unroll
      for (int hh = 0; hh < 2; hh++) {
        float y0, y1, y2, y3;
        mma0(y0, y1, y2, y3, by[0], by[1], by[2], by[3], lds32(y0a + 128 * kap + 64 * hh), lds32(y1a + 128 * kap + 64 * hh));
        x5[kap][hh] = pack_bf(y0, y1);
        x3[kap][hh] = pack_bf(y2, y3);
      }
    };
    ygen(11); ygen(10); ygen(9); ygen(8);
#pragma unroll
    for (int kap = 11; kap >= 0; kap--) {
      if (kap >= 4) ygen(kap - 4);
#pragma unroll
      for (int sg = 0; sg < 2; sg++)
#pragma unroll
        for (int i = 4; i >= 0; i--) {
          const int be = kap + 4 + i;
          if (be <= 15) {
            const uint2 &hi = sg ? a3[2 * i + 1] : a5[2 * i + 1], &lo = sg ? a3[2 * i] : a5[2 * i];
            const uint32_t b0 = sg ? x3[kap][0] : x5[kap][0], b1 = sg ? x3[kap][1] : x5[kap][1];
            if (be < 8 && i == 0 && sg == 0) mma0(acc[be][0], acc[be][1], acc[be][2], acc[be][3], hi.x, hi.y, lo.x, lo.y, b0, b1);
            else mma(acc[be][0], acc[be][1], acc[be][2], acc[be][3], hi.x, hi.y, lo.x, lo.y, b0, b1);
          }
        }
    }
  }
  TS(45);
  {
    const uint32_t st = tb + T_ST + lane * 8;
#pragma unroll
    for (int be = 4; be < 12; be++) sts64(st + 256 * be, pack_bf(acc[be][0], acc[be][1]), pack_bf(acc[be][2], acc[be][3]));
    SPLIT();
    uint32_t F[66], qd[8][4];
    const uint32_t fa = tb + T_D + 32 + 4 * x;
#pragma unroll
    for (int i = 0; i < 32; i++) {
      const int s = 120 - (i >> 2) - 8 * (i & 3);
      uint32_t(&q)[4] = qd[i & 7];
      ldsm4(q, qa + 16 * s);
      const int m = 16 * (i & 3) + 2 * (i >> 2);
      F[m] = lds32(fa + 32 * m); F[m + 1] = lds32(fa + 32 * m + 32);
#pragma unroll
      for (int be = 15; be >= 12; be--) {
        const int de = 8 * be - s;
        float(&a)[4] = (be >= 14 && !(i & 1)) ? acc[be - 4] : acc[be];
        if (de >= 0 && be >= 14 && i == 2 * (15 - be)) mma0(a[0], a[1], a[2], a[3], q[0], q[1], q[2], q[3], F[2 * de + 1], F[2 * de]);
        else if (de >= 0) mma(a[0], a[1], a[2], a[3], q[0], q[1], q[2], q[3], F[2 * de + 1], F[2 * de]);
      }
    }
#pragma unroll
    for (int i = 0; i < 8; i++) acc[14 + (i >> 2)][i & 3] += acc[10 + (i >> 2)][i & 3];
    F[64] = lds32(fa + 32 * 64); F[65] = lds32(fa + 32 * 65);
    uint32_t qp = qa + 128 * 11, sta = st + 256 * 10;
    uint4* yd = ydst + 7 * 32;
#pragma unroll
    for (int i = 0; i < 6; i++) ldsm4(qd[i], qp - 16 * i);
    uint2 sv = lds64(sta + 256);
    float ci[4] = {bf_lo(sv.x), bf_hi(sv.x), bf_lo(sv.y), bf_hi(sv.y)};
    float T[5][4];
#pragma unroll
    for (int i = 0; i < 16; i++) T[i >> 2][i & 3] = acc[12 + (i >> 2)][i & 3];
    nb_sync(NB_YZ, 160);
    TS(46);
#pragma unroll 1
    for (int bp = 5; bp >= 0; bp--) {
      uint32_t held[2];
#pragma unroll
      for (int o = 1; o >= 0; o--) {
#pragma unroll
        for (int k = 4; k >= 1; k--) mmac(T[k], qd[0][0], qd[0][1], qd[0][2], qd[0][3], F[16 * k + 1], F[16 * k], T[k - 1]);
        mmac(T[0], qd[0][0], qd[0][1], qd[0][2], qd[0][3], F[1], F[0], ci);
        ldsm4(qd[6], qp - 16 * 6);
        ldsm4(qd[7], qp - 16 * 7);
        sv = lds64(sta);
#pragma unroll
        for (int i = 1; i < 8; i++) {
#pragma unroll
          for (int k = 3; k >= 0; k--)
            mma(T[k][0], T[k][1], T[k][2], T[k][3], qd[i][0], qd[i][1], qd[i][2], qd[i][3], F[16 * k + 2 * i + 1], F[16 * k + 2 * i]);
          if (i < 7) ldsm4(qd[i - 1], qp - 128 - 16 * (i - 1));
          if (i == 2) {
            const uint32_t w0 = pack_bf(T[4][0], T[4][1]), w1 = pack_bf(T[4][2], T[4][3]);
            if (o) { held[0] = w0; held[1] = w1; }
            else st_x(yd, nz(w0), w1, held[0], held[1]);
          }
          if (i == 4) {
            if (2 * bp + o <= 4) sv = make_uint2(0, 0);
            ci[0] = bf_lo(sv.x); ci[1] = bf_hi(sv.x); ci[2] = bf_lo(sv.y); ci[3] = bf_hi(sv.y);
          }
        }
        qp -= 128; sta -= 256;
      }
      yd -= 32;
      if (!(bp & 1)) nb_arrive(NB_Y + 1 + (bp >> 1), 160);
    }
#pragma unroll
    for (int B = 1; B >= 0; B--)
      st_x(ydst + B * 32, nz(pack_bf(T[2 * B][0], T[2 * B][1])), pack_bf(T[2 * B][2], T[2 * B][3]),
           pack_bf(T[2 * B + 1][0], T[2 * B + 1][1]), pack_bf(T[2 * B + 1][2], T[2 * B + 1][3]));
  }
}

__device__ __forceinline__ void dual_exp(const uint32_t* w, uint32_t* e) {
  const float L = 1.44268798828125f;
  uint32_t mx = bmax2(bmax2(w[0], w[1]), bmax2(w[2], w[3]));
  uint32_t mn = bmin2(bmin2(w[0], w[1]), bmin2(w[2], w[3]));
  mx = bmax2(mx, __shfl_xor_sync(0xffffffffu, mx, 1));
  mn = bmin2(mn, __shfl_xor_sync(0xffffffffu, mn, 1));
  mx = bmax2(mx, __shfl_xor_sync(0xffffffffu, mx, 2));
  mn = bmin2(mn, __shfl_xor_sync(0xffffffffu, mn, 2));
  const float mx0 = bf_lo(mx) * -L, mx1 = bf_hi(mx) * -L, mn0 = bf_lo(mn) * L, mn1 = bf_hi(mn) * L;
#pragma unroll
  for (int i = 0; i < 2; i++) {
    const float a0 = bf_lo(w[2 * i]), a1 = bf_hi(w[2 * i]), b0 = bf_lo(w[2 * i + 1]), b1 = bf_hi(w[2 * i + 1]);
    e[2 * i] = pack_bf(ex2(fmaf(a0, L, mx0)), ex2(fmaf(b0, L, mx0)));
    e[2 * i + 1] = pack_bf(ex2(fmaf(a1, L, mx1)), ex2(fmaf(b1, L, mx1)));
    e[4 + 2 * i] = pack_bf(ex2(fmaf(a0, -L, mn0)), ex2(fmaf(b0, -L, mn0)));
    e[5 + 2 * i] = pack_bf(ex2(fmaf(a1, -L, mn1)), ex2(fmaf(b1, -L, mn1)));
  }
}
__device__ __forceinline__ void normalise(uint32_t* e, const float (&s)[4]) {
  const uint32_t r = pack_bf(rcp(s[0]), rcp(s[2]));
  const __nv_bfloat162 rr = *(const __nv_bfloat162*)&r;
#pragma unroll
  for (int i = 0; i < 4; i++) {
    const __nv_bfloat162 v = __hmul2(*(const __nv_bfloat162*)&e[i], (i & 1) ? __high2bfloat162(rr) : __low2bfloat162(rr));
    e[i] = *(const uint32_t*)&v;
  }
}
__host__ __device__ constexpr uint64_t qdesc(uint32_t addr) { return mkdesc(addr, 128, 256, 0); }

__global__ void __launch_bounds__(NTHREADS, 1)
fused_kernel(const Params P, const __grid_constant__ CUtensorMap mx, const __grid_constant__ CUtensorMap mw,
             const __grid_constant__ CUtensorMap mo, const __grid_constant__ CUtensorMap mu,
             const __grid_constant__ CUtensorMap mout, const __grid_constant__ CUtensorMap mw4) {
  constexpr uint32_t sb = SB;
  const int tid = threadIdx.x, lane = tid & 31;
  const int warp = __shfl_sync(0xffffffffu, tid >> 5, 0);
  const int b = blockIdx.x, oct = b >> 3, i8 = b & 7;
  const int rt = (((oct & 4) ? ~oct : oct) & 3) * 2 + (i8 >> 2);
  const int hp = (oct >> 2) * 4 + (i8 & 3);

  const int wg = warp >> 2, w = warp & 3;
  const int d = b * 4 + ((tid >> 5) & 3);
  const KgenRaw raw = kgen_load(P, d, tid >> 7, lane);
  const unsigned short dsk = __ldg((const unsigned short*)P.Dskip + d);
  if (warp == 15) {
    asm volatile("prefetch.tensormap [%0];" ::"l"(&mu) : "memory");
    asm volatile("prefetch.tensormap [%0];" ::"l"(&mw) : "memory");
    asm volatile("prefetch.tensormap [%0];" ::"l"(&mx) : "memory");
    asm volatile("prefetch.tensormap [%0];" ::"l"(&mw4) : "memory");
  }
  if (warp == 12) {
    if (lane == 0) {
#pragma unroll
      for (int i = 0; i < 9; i++) mbar_init(BAR(i), 1);
      asm volatile("fence.mbarrier_init.release.cluster;" ::: "memory");
    }
    __syncwarp();
    if (lane < 9) mbar_expect(BAR(0) + 8 * lane, (lane == 5 || lane == 7) ? 40960 : ((lane == 0 || lane > 5) ? 16384 : 28672));
    __syncwarp();
    e_tma3d(sb + OFF_W, &mw, BAR(MB_FULL), hp * 32, 0, 0);
    e_tma2d(sb + OFF_X + 3 * 16384, &mx, BAR(MB_FULL), 0, rt * 256);
    nb_arrive(NB_PROD, 512);
  } else if (warp == 14) {
    e_prefetch(P.x + (size_t)(rt * 256 + hp * 8) * 512, 8192);
  } else if (warp == 13) {
    if (lane == 0) {
#pragma unroll
      for (int i = 9; i < 39; i++) mbar_init(BAR(i), i < MB_EMPTY ? 1 : 4);
      asm volatile("fence.mbarrier_init.release.cluster;" ::: "memory");
    }
    __syncwarp();
    if (lane < 13 && lane != 9) mbar_expect(BAR(MB_FULL + 8) + 8 * lane, lane < 8 ? 16384 : (lane == 8 ? 131072 : (lane == 10 ? 8192 : (lane == 11 ? 24576 : 32768))));
    nb_arrive(NB_PROD, 512);
  }
  const uint32_t tb = sb + OFF_T + w * T_CH;
  const uint32_t kp = wg == 2 ? sb + OFF_STG0 + 16384 + w * 1024 : ((tb + 127) & ~127u) + (wg == 3 ? 2 : wg) * 1536;
  const KgenAddr kad = kgen_addr(lane, kp);
  if ((warp >> 1) != 6) nb_sync(NB_PROD, 512);
  else nb_sync(NB_GATE + 1, 64);
  if (warp == 12) {
#pragma unroll 1
    for (int kb = 1; kb < 4; kb++) {
      if (kb == U_AT) e_tma4d(sb + OFF_STG0, &mu, BAR(MB_URAW), i8 * 64, oct * 2);
      e_tma3d(sb + OFF_W + kb * 12288, &mw, BAR(MB_FULL) + 8 * kb, hp * 32, kb * 64, 0);
      e_tma2d(sb + OFF_X + (kb < 2 ? kb + 3 : kb - 2) * 16384, &mx, BAR(MB_FULL) + 8 * kb, kb * 64, rt * 256);
    }
    e_tma4d(sb + OFF_W + 4 * 12288, &mw4, BAR(MB_FULL + 4), hp * 32, 4);
    e_tma2d(sb + OFF_X + 2 * 16384, &mx, BAR(MB_FULL + 4), 256, rt * 256);
    e_tma4d(sb + OFF_W + 6 * 12288, &mw4, BAR(MB_FULL + 6), hp * 32, 6);
    if (smem_u32(smem_raw) != SB) __trap();
    if (lane == 0) TS1(54);
  }
  float k[5][4], k2048, ksc;
  kgen_unit(raw, kad, blockIdx.y, k, k2048, ksc);
  TS(40 + wg);
  if ((fu(k[0][0]) & fu(k[1][0]) & fu(k[2][0]) & fu(k[3][0]) & fu(k[4][0])) == 0xffffffffu) sts32(kp, 0);
  if (wg) nb_arrive(0, 512);
  k2048 += __shfl_xor_sync(0xffffffffu, k2048, 16);
  k2048 += __shfl_xor_sync(0xffffffffu, k2048, 8);
  if (wg != 2) {
    uint32_t h[10];
#pragma unroll
    for (int j = 0; j < 10; j++) h[j] = hu(__floats2half2_rn(k[j >> 1][2 * (j & 1)], k[j >> 1][2 * (j & 1) + 1]));
    sts128(kp + lane * 16, h[0], h[1], h[2], h[3]);
    sts128(kp + 512 + lane * 16, h[4], h[5], h[6], h[7]);
    sts128(kp + 1024 + lane * 16, h[8], h[9], fu(k2048), fu(ksc));
  }
  if (wg == 0) { nb_arrive(NB_PREP, 512); nb_sync(0, 512); }
  else if (wg != 2) nb_arrive(NB_PREP, 512);
  else nb_sync(NB_PREP, 512);
  if (warp >= 12) {
    asm volatile("setmaxnreg.dec.sync.aligned.u32 32;");
    if (warp == 12) {
      if (X2_AT < 0) e_prefetch(P.x + (size_t)(rt * 256 + 128 + hp * 8) * 512, 8192);
      uint32_t slot = sb + OFF_X + 3 * 16384;
#pragma unroll 1
      for (int n = 0; n < 11; n++) {
        mbar_spin(BAR(MB_EMPTY) + 8 * n);
        const int m = n + 5;
        e_tma2d(slot, &mx, BAR(MB_FULL) + 8 * m, (m & 7) * 64, rt * 256 + (m >> 3) * 128);
        slot = slot == sb + OFF_X + 4 * 16384 ? sb + OFF_X : slot + 16384;
        if (n == X2_AT) e_prefetch(P.x + (size_t)(rt * 256 + 128 + hp * 8) * 512, 8192);
        if (n == 7) {
          e_prefetch(P.wo + (size_t)b * 2048, 4096);
          asm volatile("prefetch.tensormap [%0];" ::"l"(&mo) : "memory");
          asm volatile("prefetch.tensormap [%0];" ::"l"(&mout) : "memory");
        }
      }
#pragma unroll 1
      for (int i = 0; i < 8; i++) {
        mbar_wait(BAR(MB_EMPTY + 10) + 8 * ((0x54332222u >> (4 * i)) & 7));
        const int w0 = (0x54736210u >> (4 * i)) & 7;
        e_tma3d(sb + OFF_W + w0 * 16384, &mo, BAR(MB_WO), 0, w0 * 64, (hp & 3) * 2);
      }
    } else {
      if (warp == 15) {
        const uint4 v0 = __ldg((const uint4*)P.wphi + hp * 64 + lane), v1 = __ldg((const uint4*)P.wphi + hp * 64 + 32 + lane);
        sts128(sb + OFF_PHI + (lane & 1) * 256 + (lane >> 1) * 16, v0.x, v0.y, v0.z, v0.w);
        sts128(sb + OFF_PHI + 512 + (lane & 1) * 256 + (lane >> 1) * 16, v1.x, v1.y, v1.z, v1.w);
        const uint32_t one = (((lane >> 3) ^ (lane >> 4)) & 1) ? 0u : ((lane & 1) ? 0x3F800000u : 0x3F80u);
        const int q = (lane >> 1) & 3;
        sts128(sb + OFF_EYE + lane * 16, q == 0 ? one : 0u, q == 1 ? one : 0u, q == 2 ? one : 0u, q == 3 ? one : 0u);
        sts64(sb + OFF_ONE + lane * 8, 0x3F803F80u, 0x3F803F80u);
        asm volatile("fence.proxy.async.shared::cta;" ::: "memory");
        nb_arrive(NB_KREAD, 160);
      }
      uint32_t* cnt = (uint32_t*)(P.xs + X_CNT) + (warp == 13 ? i8 : (warp == 14 ? 8 + rt : 16 + oct)) * 32;
      const unsigned target = (ld_x32(cnt) & ~15u) + 16;
      if (warp != 14) {
        if (warp == 15) mbar_wait(BAR(MB_EMPTY + ZERO_STEP));
        uint4* pz = P.xs + (warp == 13 ? X_PART + (hp * 8 + rt) * 144 : X_Y + b * 1024) + lane;
#pragma unroll 1
        for (int i = (warp == 13 ? 144 : 1024) - lane; i > 0; i -= 32, pz += 32) st_x(pz, 0, 0, 0, 0);
      }
      if (warp == 15) __syncwarp();
      else nb_sync(warp == 13 ? NB_INIT : NB_ODONE, warp == 13 ? 160 : 288);
      if (lane == 0) asm volatile("red.release.gpu.global.add.u32 [%0], %1;" ::"l"(cnt), "r"(warp == 15 ? 2 : 1) : "memory");
      if (lane == 0) TS1(warp == 13 ? 50 : (warp == 14 ? 57 : 53));
      asm volatile("fence.proxy.async.shared::cta;" ::: "memory");
      if (warp == 13) cnt += ((lane & 1 ? b >> 4 : i8 ^ (lane & 4)) - i8) * 32;
#pragma unroll 1
      for (int i = 0; i < SPIN_MAX; i++) {
        unsigned v;
        asm volatile("ld.acquire.gpu.global.u32 %0, [%1];" : "=r"(v) : "l"(cnt) : "memory");
        if (__all_sync(0xffffffffu, (int)(v - target) >= 0)) break;
      }
      if (lane == 0) TS1(warp == 13 ? 51 : (warp == 14 ? 58 : 55));
      if (warp == 15) { nb_arrive(NB_YZ, 160); return; }
      asm volatile("fence.proxy.async.global;" ::: "memory");
      if (warp == 13) {
        mbar_wait(BAR(MB_EMPTY + 11));
        e_expect(BAR(MB_UFULL), 4 * U_CH);
        e_bulk(sb + OFF_U, P.xs + X_UT + b * (U_CH / 4), 4 * U_CH, BAR(MB_UFULL));
      } else {
        const uint4* src = P.xs + X_O + (rt * 4 + (hp >> 2)) * 4096;
        e_bulk(sb + OFF_X + 32768 + 57344, src + 3584, 8192, BAR(MB_OA));
        e_bulk(sb + OFF_X + 32768, src, 32768, BAR(MB_OC));
        e_bulk(sb + OFF_STG0, src + 3200, 6144, BAR(MB_OB));
        nb_sync(NB_BDONE, 288);
        asm volatile("fence.proxy.async.shared::cta;" ::: "memory");
        e_bulk(sb + OFF_U, src + 2048, 18432, BAR(MB_OB));
      }
    }
    return;
  }

  const int t = tid & 127;
  const int g = lane >> 2, c = lane & 3;
  if (wg == 1) {
    mbar_wait(BAR(MB_URAW));
    TS(48);
    uint4* dst = P.xs + X_UT + (i8 * 64 + g) * (U_CH / 16) + (w & 1) * (U_ODD / 16) + U_PAD / 16 + oct * 8 + (w >> 1) * 4 + c;
    const int ln = ((lane >> 1) & 3) + 4 * (lane & 1);
    uint32_t r[8][4];
#pragma unroll
    for (int i = 0; i < 8; i++) ldsm4t(r[i], sb + OFF_STG0 + w * 4096 + ((lane >> 3) * 8 + ln) * 128 + ((i ^ ln) << 4));
#pragma unroll
    for (int i = 0; i < 8; i++) dst[i * (U_CH / 2)] = make_uint4(r[i][0], r[i][1], r[i][2], r[i][3]);
    nb_arrive(NB_INIT, 160);
    if (lane == 0) mbar_arrive(BAR(MB_AUX));
  }
  {
    if (wg == 2) {
      asm volatile("setmaxnreg.inc.sync.aligned.u32 160;");
#pragma unroll
      for (int j = 0; j < 5; j++) { k[j][0] *= ksc; k[j][1] *= ksc; k[j][2] *= ksc; k[j][3] *= ksc; }
#pragma unroll 1
      for (int q = 0; q < 3; q++) {
        const uint32_t src = ((tb + 127) & ~127u) + q * 1536 + lane * 16;
        const uint4 v0 = lds128(src), v1 = lds128(src + 512), v2 = lds128(src + 1024);
        const uint32_t h[10] = {v0.x, v0.y, v0.z, v0.w, v1.x, v1.y, v1.z, v1.w, v2.x, v2.y};
#pragma unroll
        for (int j = 0; j < 10; j++) {
          const float2 f = __half22float2(*(const __half2*)&h[j]);
          k[j >> 1][2 * (j & 1)] = fmaf(f.x, uf(v2.w), k[j >> 1][2 * (j & 1)]);
          k[j >> 1][2 * (j & 1) + 1] = fmaf(f.y, uf(v2.w), k[j >> 1][2 * (j & 1) + 1]);
        }
        k2048 += uf(v2.z);
      }
#pragma unroll
      for (int o2 = 4; o2; o2 >>= 1) k2048 += __shfl_xor_sync(0xffffffffu, k2048, o2);
      if (lane == 0) k[0][0] += bf_lo(dsk);
      __syncwarp();
      TS(34);
      build_tables(tb, lane, k, k2048);
      TS(35);
      uint4* const g_y = P.xs + X_Y;
      conv_channel(sb + OFF_U + w * U_CH, tb, lane, g_y + (size_t)d * 256 + lane);
      nb_arrive(NB_BDONE, 288);
      nb_arrive(NB_Y, 160);
      TS(37);
      if (w == 0) TSDUMP(32);
      return;
    }
    if (wg == 1) {
      mbar_wait(BAR(MB_EMPTY + 4));
      mbar_spin(BAR(MB_EMPTY + 6));
    }
    TS(wg * 16 + 1);
  }

  float acc[2][48];
  {
    uint32_t fb = BAR(MB_FULL) + 64 * wg;
    uint32_t da = (uint32_t)mkdesc(sb + OFF_X, 16, 0, 0) + (wg ? 1024 : 3072), db = (uint32_t)mkdesc(sb + OFF_W, 4096, 0, 0);
    constexpr uint64_t ha = mkdesc(0, 0, 1024, 1), hb = mkdesc(0, 0, 512, 2);
    mbar_spin(fb);
    TS(wg * 16 + 2);
#pragma unroll 1
    for (int kb = 0; kb < 8; kb++) {
      WG_FENCE();
#pragma unroll
      for (int k = 0; k < 4; k++) {
        wgmma_ss_n96(acc[0], ha | (da + 2 * k), hb | (db + 64 * k), k ? 1 : kb);
        wgmma_ss_n96(acc[1], ha | (da + 2 * k + 512), hb | (db + 64 * k), k ? 1 : kb);
      }
      WG_COMMIT();
      if (kb < 7) mbar_spin(fb + 8);
      WG_WAIT(1);
      if (kb > 0) e_arrive(fb + 8 * (MB_EMPTY - MB_FULL - 1));
      fb += 8; db += 768;
      da = da == (uint32_t)mkdesc(sb + OFF_X + 65536, 16, 0, 0) ? da - 4096 : da + 1024;
    }
    if (wg == 0) nb_sync(NB_KREAD, 160);
    asm volatile("setmaxnreg.inc.sync.aligned.u32 160;");
    WG_WAIT(0);
    e_arrive(fb + 8 * (MB_EMPTY - MB_FULL - 1));
    SPLIT();
  }
  TS(wg * 16 + 3);

  constexpr uint32_t stg0 = sb + OFF_STG0, stg1 = sb + OFF_X + 32768;
  uint4* const g_part = P.xs + X_PART;
  uint4* const g_o = P.xs + X_O;
  constexpr uint32_t kvs = stg0;
  auto pack8 = [](const float* a) { return make_uint4(pack_bf(a[0], a[1]), pack_bf(a[2], a[3]), pack_bf(a[4], a[5]), pack_bf(a[6], a[7])); };
  auto feat = [&](const uint4 (&af)[4], float (&p)[4][8]) {
    WG_FENCE();
#pragma unroll
    for (int u = 0; u < 4; u++) wgmma_rs_n16(p[u], af[u], qdesc(sb + OFF_PHI + (u & 1) * 512), 0);
    WG_COMMIT();
  };
  auto packp = [](const float (&p)[4][8], uint32_t (&pw)[16]) {
#pragma unroll
    for (int i = 0; i < 16; i++) pw[i] = pack_bf(p[i >> 2][(i & 1) + 2 * (i & 2)], p[i >> 2][(i & 1) + 2 * (i & 2) + 2]);
  };
  auto contract = [&](float (&kc)[20], uint32_t stg, int acc_in) {
    WG_FENCE();
#pragma unroll
    for (int s = 0; s < 8; s++) wgmma_ss_n40(kc, qdesc(stg + s * SLAB), qdesc(stg + s * SLAB + 2048), s ? 1 : acc_in);
    WG_COMMIT();
    WG_WAIT(0);
  };
  uint32_t eq[32];
  {
    uint4 af[4], aq[4], vp[4];
    float p[4][8];
#pragma unroll
    for (int u = 0; u < 4; u++) af[u] = pack8(acc[u >> 1] + 16 + 8 * (u & 1));
    feat(af, p);
#pragma unroll
    for (int u = 0; u < 4; u++) { aq[u] = pack8(acc[u >> 1] + 8 * (u & 1)); vp[u] = pack8(acc[u >> 1] + 32 + 8 * (u & 1)); }
    WG_WAIT(0);
    uint32_t pw[16], ek[32];
    packp(p, pw);
#pragma unroll
    for (int u = 0; u < 4; u++) dual_exp(pw + 4 * u, ek + 8 * u);
    TS(wg * 16 + 12);
    mbar_spin(wg ? BAR(MB_EMPTY + 15) : BAR(MB_AUX));
    float rs[8][4];
    WG_FENCE();
#pragma unroll
    for (int i = 0; i < 8; i++) wgmma_rs_n8(rs[i], make_uint4(ek[4 * i], ek[4 * i + 1], ek[4 * i + 2], ek[4 * i + 3]), qdesc(sb + OFF_ONE), 0);
    WG_COMMIT();
    feat(aq, p);
    const uint32_t sl = (wg ? stg1 : stg0) + w * SLAB + lane * 16;
#pragma unroll
    for (int i = 0; i < 4; i++) stsm4(sl + (i >> 1) * 4 * SLAB + 2048 + (i & 1) * 512, vp[i].x, vp[i].y, vp[i].z, vp[i].w);
    sts128(sl + (lane >> 4) * (4 * SLAB - 256) + 3072, 0x3F803F80u, 0x3F803F80u, 0x3F803F80u, 0x3F803F80u);
    WG_WAIT(1);
#pragma unroll
    for (int i = 0; i < 8; i++) {
      normalise(ek + 4 * i, rs[i]);
      stsm4(sl + (i >> 2) * 4 * SLAB + (i & 3) * 512, ek[4 * i], ek[4 * i + 1], ek[4 * i + 2], ek[4 * i + 3]);
    }
    asm volatile("fence.proxy.async.shared::cta;" ::: "memory");
    TS(wg * 16 + 13);
    if (wg) {
      nb_arrive(NB_ST0, 256);
    } else {
      float kc[20];
      uint4* pp = g_part + (size_t)(hp * 8 + rt) * 144 + t;
      uint32_t* pz = (uint32_t*)(pp - t + 128) + w * 16 + c * 8 + g;
      asm volatile("" : "+l"(pp), "+l"(pz));
      nb_sync(NB_WG0, 128);
      contract(kc, stg0, 0);
      mbar_wait(BAR(MB_UFULL));
      TS(15);
      nb_sync(NB_ST0, 256);
      contract(kc, stg1, 1);
      TS(6);
      float kv[8];
#pragma unroll
      for (int i = 0; i < 8; i++) kv[i] = w & 2 ? kc[8 + i] : kc[i];
      st_x(pp, nz(pack_bf(kv[0], kv[1])), pack_bf(kv[2], kv[3]), pack_bf(kv[4], kv[5]), pack_bf(kv[6], kv[7]));
      if (c < 2) st_x32(pz, nz(fu(c ? kc[18] : kc[16])));
      TS(5);
    }
    SPLIT();
    WG_WAIT(0);
    packp(p, pw);
#pragma unroll
    for (int u = 0; u < 4; u++) dual_exp(pw + 4 * u, eq + 8 * u);
    SPLIT();
  }
  TS(wg * 16 + 4);
  if (wg == 1) {
    mbar_wait(BAR(MB_UFULL));
    const uint4* ps = g_part + (size_t)hp * 8 * 144 + t;
    const uint32_t* zs = (const uint32_t*)(g_part + (size_t)(hp * 8 + (lane >> 4) * 4) * 144 + 128) + w * 16 + (lane & 15);
    uint4 v[8];
    uint32_t zv[4];
#pragma unroll 1
    for (int it = 0; it < SPIN_MAX; it++) {
#pragma unroll
      for (int i = 0; i < 8; i++) v[i] = ld_x(ps + i * 144);
#pragma unroll
      for (int i = 0; i < 4; i++) zv[i] = ld_x32(zs + i * 576);
      uint32_t m = min(min(zv[0], zv[1]), min(zv[2], zv[3]));
#pragma unroll
      for (int i = 0; i < 8; i++) m = min(m, v[i].x);
      if (__all_sync(0xffffffffu, m != 0)) break;
    }
    float s[8];
    WG_FENCE();
#pragma unroll
    for (int r = 0; r < 8; r++) wgmma_rs_n16(s, v[r], qdesc(sb + OFF_EYE), r);
    WG_COMMIT();
    float zsum = (uf(zv[0]) + uf(zv[1])) + (uf(zv[2]) + uf(zv[3]));
    zsum += __shfl_xor_sync(0xffffffffu, zsum, 16);
    const uint32_t z1 = pack_bf(zsum, 1.f);
    if (lane < 16) sts128(kvs + w * 768 + 512 + lane * 16, z1, z1, z1, z1);
    WG_WAIT(0);
    stsm4(kvs + w * 768 + lane * 16, pack_bf(s[0], s[1]), pack_bf(s[2], s[3]), pack_bf(s[4], s[5]), pack_bf(s[6], s[7]));
    asm volatile("fence.proxy.async.shared::cta;" ::: "memory");
    TS(22);
  }
  nb_sync(NB_KV, 256);
  {
    float n[8][12];
    WG_FENCE();
#pragma unroll
    for (int i = 0; i < 8; i++) wgmma_rs_n24(n[i], make_uint4(eq[4 * i], eq[4 * i + 1], eq[4 * i + 2], eq[4 * i + 3]), qdesc(kvs + (i & 3) * 768), 0);
    WG_COMMIT();
    uint32_t* od = (uint32_t*)(g_o + (size_t)((rt * 4 + wg * 2) * 32 + hp * 2) * 128) + w * 64 + lane;
    WG_WAIT(0);
#pragma unroll
    for (int u = 0; u < 4; u++) {
      float(&np)[12] = n[2 * u];
      const float(&nm)[12] = n[2 * u + 1];
      const float q0 = np[9] * rcp(nm[9]), q1 = np[11] * rcp(nm[11]);
      const float r0 = rcp(fmaf(nm[8], q0, fmaf(np[9], 1e-6f, np[8]))), r1 = rcp(fmaf(nm[10], q1, fmaf(np[11], 1e-6f, np[10])));
#pragma unroll
      for (int i = 0; i < 8; i++) np[i] = fmaf(nm[i], (i & 2) ? q1 : q0, np[i]);
      uint32_t* o = od + (u >> 1) * 16384 + (u & 1) * 512;
      o[0] = pack_bf(np[0] * r0, np[1] * r0);
      o[32] = pack_bf(np[2] * r1, np[3] * r1);
      o[256] = pack_bf(np[4] * r0, np[5] * r0);
      o[288] = pack_bf(np[6] * r1, np[7] * r1);
      if (u == 1) SPLIT();
    }
  }
  TS(wg * 16 + 7);
  nb_arrive(NB_ODONE, 288);
  if (wg) {
    const uint4* src = P.xs + X_Y + (oct * 32 + c * 8) * 256 + (2 * w + (g >> 2)) * 32 + i8 * 4 + (g & 3);
    __nv_bfloat16* dst = P.out + (size_t)((2 * w + (g >> 2)) * 256 + i8 * 16 + (g & 3) * 2) * 1024 + 512 + oct * 32 + c * 8;
    nb_sync(NB_Y + w, 160);
    uint4 v[8];
#pragma unroll 1
    for (int it = 0; it < SPIN_MAX; it++) {
      uint32_t m = 0xffffffffu;
#pragma unroll
      for (int i = 0; i < 8; i++) v[i] = ld_x(src + i * 256);
#pragma unroll
      for (int i = 0; i < 8; i++) m = min(m, v[i].x);
      if (__all_sync(0xffffffffu, m != 0)) break;
    }
#pragma unroll
    for (int i = 0; i < 8; i++) *(uint4*)(dst + (size_t)((i >> 2) * 128 + ((i >> 1) & 1) * 8 + (i & 1)) * 1024) = tr_row(v, i);
    TS(31);
    GT(63);
    if (w == 0) TSDUMP(16);
    return;
  }
  mbar_wait(BAR(MB_WO));
  nb_sync(NB_BDONE, 288);
  TS(8);
  mbar_spin(BAR(MB_OA));
  TS(9);
  float oc[64];
  {
    constexpr uint64_t ha = mkdesc(0, 0, 128, 0), hb = mkdesc(0, 0, 1024, 1);
    constexpr uint32_t da0 = (uint32_t)mkdesc(stg1, 1024, 0, 0), db0 = (uint32_t)mkdesc(sb + OFF_W, 8192, 0, 0);
#pragma unroll 1
    for (int j = 0; j < 8; j++) {
      const int kb = (j + 7) & 7;
      if ((j & 3) == 1) mbar_spin(j == 1 ? BAR(MB_OC) : BAR(MB_OB));
      WG_FENCE();
#pragma unroll
      for (int k = 0; k < 4; k++) wgmma_ss_n128(oc, ha | (da0 + 512 * kb + 128 * k), hb | (db0 + 1024 * kb + 128 * k), k ? 1 : j);
      WG_COMMIT();
    }
    WG_WAIT(0);
  }
  TS(10);
  const uint32_t ot = ((sb + OFF_T + 1023) & ~1023u) + w * 4096;
#pragma unroll
  for (int hf = 0; hf < 2; hf++) {
#pragma unroll
    for (int i = 8 * hf; i < 8 * hf + 8; i += 2)
      stsm4(ot + hf * 2048 + (lane & 15) * 128 + (((i + (lane >> 4)) ^ lane) & 7) * 16, pack_bf(oc[4 * i], oc[4 * i + 1]),
            pack_bf(oc[4 * i + 2], oc[4 * i + 3]), pack_bf(oc[4 * i + 4], oc[4 * i + 5]), pack_bf(oc[4 * i + 6], oc[4 * i + 7]));
    asm volatile("fence.proxy.async.shared::cta;" ::: "memory");
    __syncwarp();
    e_store2d(&mout, ot + hf * 2048, (hp & 3) * 128 + hf * 64, (rt * 4 + (hp >> 2)) * 64 + w * 16);
  }
  asm volatile(ELECT "cp.async.bulk.commit_group;\n@p cp.async.bulk.wait_group.read 0;\n}\n" ::: "memory");
  TS(wg * 16 + 11);
  GT(61 + wg);
  if (w == 0) TSDUMP(0);
  if (w == 1) TSDUMP(48);
}

typedef CUresult (*EncodeFn)(CUtensorMap*, CUtensorMapDataType, cuuint32_t, void*, const cuuint64_t*, const cuuint64_t*,
                             const cuuint32_t*, const cuuint32_t*, CUtensorMapInterleave, CUtensorMapSwizzle,
                             CUtensorMapL2promotion, CUtensorMapFloatOOBfill);

}

extern "C" void kernel_launch(void* const* d_in, const int* in_sizes, int n_in, void* d_out, int out_size) {
  (void)in_sizes; (void)n_in; (void)out_size;
  void* fn = nullptr;
  cudaDriverEntryPointQueryResult qr;
  cudaGetDriverEntryPoint("cuTensorMapEncodeTiled", &fn, cudaEnableDefault, &qr);
  EncodeFn enc = (EncodeFn)fn;
  CUtensorMap mx, mw, mo, mu, mout, mw4;
  const cuuint32_t es[5] = {1, 1, 1, 1, 1};
  {
    cuuint64_t dims[2] = {512, 2048}, st[1] = {1024};
    cuuint32_t box[2] = {64, 128};
    enc(&mx, CU_TENSOR_MAP_DATA_TYPE_BFLOAT16, 2, d_in[0], dims, st, box, es, CU_TENSOR_MAP_INTERLEAVE_NONE,
        CU_TENSOR_MAP_SWIZZLE_128B, CU_TENSOR_MAP_L2_PROMOTION_L2_128B, CU_TENSOR_MAP_FLOAT_OOB_FILL_NONE);
  }
  {
    cuuint64_t dims[3] = {512, 512, 3}, st[2] = {3072, 1024};
    cuuint32_t box[3] = {32, 64, 3};
    enc(&mw, CU_TENSOR_MAP_DATA_TYPE_BFLOAT16, 3, d_in[1], dims, st, box, es, CU_TENSOR_MAP_INTERLEAVE_NONE,
        CU_TENSOR_MAP_SWIZZLE_64B, CU_TENSOR_MAP_L2_PROMOTION_L2_128B, CU_TENSOR_MAP_FLOAT_OOB_FILL_NONE);
  }
  {
    cuuint64_t dims[3] = {64, 512, 8}, st[2] = {1024, 128};
    cuuint32_t box[3] = {64, 64, 2};
    enc(&mo, CU_TENSOR_MAP_DATA_TYPE_BFLOAT16, 3, d_in[3], dims, st, box, es, CU_TENSOR_MAP_INTERLEAVE_NONE,
        CU_TENSOR_MAP_SWIZZLE_128B, CU_TENSOR_MAP_L2_PROMOTION_L2_128B, CU_TENSOR_MAP_FLOAT_OOB_FILL_NONE);
  }
  {
    cuuint64_t dims[4] = {512, 4, 16, 32}, st[3] = {16384, 1024, 65536};
    cuuint32_t box[4] = {64, 4, 16, 2};
    enc(&mu, CU_TENSOR_MAP_DATA_TYPE_BFLOAT16, 4, d_in[4], dims, st, box, es, CU_TENSOR_MAP_INTERLEAVE_NONE,
        CU_TENSOR_MAP_SWIZZLE_128B, CU_TENSOR_MAP_L2_PROMOTION_L2_128B, CU_TENSOR_MAP_FLOAT_OOB_FILL_NONE);
  }
  {
    cuuint64_t dims[2] = {1024, 2048}, st[1] = {2048};
    cuuint32_t box[2] = {64, 16};
    enc(&mout, CU_TENSOR_MAP_DATA_TYPE_BFLOAT16, 2, d_out, dims, st, box, es, CU_TENSOR_MAP_INTERLEAVE_NONE,
        CU_TENSOR_MAP_SWIZZLE_128B, CU_TENSOR_MAP_L2_PROMOTION_NONE, CU_TENSOR_MAP_FLOAT_OOB_FILL_NONE);
  }
  {
    cuuint64_t dims[4] = {512, 64, 3, 8}, st[3] = {3072, 1024, 64 * 3072};
    cuuint32_t box[4] = {32, 64, 3, 2};
    enc(&mw4, CU_TENSOR_MAP_DATA_TYPE_BFLOAT16, 4, d_in[1], dims, st, box, es, CU_TENSOR_MAP_INTERLEAVE_NONE,
        CU_TENSOR_MAP_SWIZZLE_64B, CU_TENSOR_MAP_L2_PROMOTION_L2_128B, CU_TENSOR_MAP_FLOAT_OOB_FILL_NONE);
  }
  Params P;
  P.x = (const __nv_bfloat16*)d_in[0];
  P.wphi = (const __nv_bfloat16*)d_in[2];
  P.wo = (const __nv_bfloat16*)d_in[3];
  P.logA = (const __nv_bfloat16*)d_in[5];
  P.Aim = (const __nv_bfloat16*)d_in[6];
  P.Cre = (const __nv_bfloat16*)d_in[7];
  P.Cim = (const __nv_bfloat16*)d_in[8];
  P.logdt = (const __nv_bfloat16*)d_in[9];
  P.Dskip = (const __nv_bfloat16*)d_in[10];
  P.out = (__nv_bfloat16*)d_out;
  cudaGetSymbolAddress((void**)&P.xs, g_x);
  P.ts = nullptr;
  cudaFuncSetAttribute(fused_kernel, cudaFuncAttributeMaxDynamicSharedMemorySize, SMEM_BYTES);
  fused_kernel<<<NCTA, NTHREADS, SMEM_BYTES>>>(P, mx, mw, mo, mu, mout, mw4);
}
```

```cpp
#include <cuda_runtime.h>
#include <cuda_bf16.h>
#include <cuda_fp16.h>
#include <cuda.h>
#include <stdint.h>

#define DBG_TS 0

namespace {

constexpr int NTHREADS = 512;
constexpr int NCTA = 128;
constexpr int OFF_W = 0;
constexpr int OFF_X = 98304;
constexpr int OFF_U = OFF_X + 65536;
constexpr int U_CH = 4416, U_ODD = 2240, U_PAD = 128;
constexpr int OFF_STG0 = OFF_U + 18432;
constexpr int SLAB = 3328;
constexpr int OFF_T = OFF_STG0 + 8 * SLAB;
constexpr int T_CH = 5216;
constexpr int T_D = 0;
constexpr int T_5 = 2144;
constexpr int T_3 = T_5 + 384;
constexpr int T_7 = T_5 + 1024;
constexpr int T_9 = T_7 + 320;
constexpr int T_KC = T_9 + 320;
constexpr int T_ST = T_5 - 1024;
constexpr int OFF_PHI = OFF_T + 4 * T_CH;
constexpr int OFF_EYE = OFF_PHI + 1024, OFF_ONE = OFF_EYE + 512;
constexpr int OFF_BAR = OFF_ONE + 256;
constexpr int SMEM_BYTES = OFF_BAR + 512 + 256 * DBG_TS;
constexpr uint32_t SB = 1024;
static_assert(T_KC + 2 * 656 <= T_CH, "table size");
static_assert(SMEM_BYTES <= 232448, "smem");
constexpr int MB_URAW = 0, MB_FULL = 1  , MB_WO = 17, MB_UFULL = 18, MB_OA = 19, MB_OB = 20, MB_OC = 21,
              MB_EMPTY = 22  , MB_AUX = 38;
__host__ __device__ constexpr uint32_t BAR(int i) { return SB + OFF_BAR + 8 * i; }
constexpr int NB_WG0 = 1, NB_ODONE = 2, NB_ST0 = 3  , NB_KV = 5, NB_YZ = 6, NB_INIT = 7, NB_PREP = 8, NB_PROD = 9, NB_KREAD = 10, NB_BDONE = 11, NB_GATE = 12,
              NB_Y = 7  ;
#define X2_AT -1
#define GATE_B 0
#define U_AT 2
#define ZERO_STEP 12
constexpr int SPIN_MAX = 1 << 16;

constexpr int X_CNT = 0;
constexpr int X_PART = 256;
constexpr int X_O = X_PART + 16 * 8 * 144;
constexpr int X_Y = X_O + 32 * 32 * 128;
constexpr int X_UT = X_Y + 512 * 8 * 32;
constexpr int X_SIZE = X_UT + 512 * (U_CH / 16);
__device__ __align__(128) uint4 g_x[X_SIZE];
extern __shared__ uint8_t smem_raw[];
#define TS(i) do {} while (0)
#define TS1(i) do {} while (0)
#define GT(i) do {} while (0)
#define TSDUMP(base) do {} while (0)

__device__ __forceinline__ uint32_t smem_u32(const void* p) { return (uint32_t)__cvta_generic_to_shared(p); }
__device__ __forceinline__ void mbar_arrive(uint32_t b) {
  asm volatile("mbarrier.arrive.shared::cta.b64 _, [%0];" ::"r"(b) : "memory");
}
__device__ __forceinline__ void mbar_wait(uint32_t b) {
  uint32_t done = 0;
#pragma unroll 1
  for (int i = 0; i < SPIN_MAX && !done; i++) {
    asm volatile("{\n.reg .pred p;\nmbarrier.try_wait.parity.shared::cta.b64 p, [%1], 0, 4000;\nselp.u32 %0, 1, 0, p;\n}\n"
                 : "=r"(done) : "r"(b) : "memory");
  }
}
__device__ __forceinline__ void mbar_spin(uint32_t b) {
  uint32_t done = 0;
#pragma unroll 1
  for (int i = 0; i < (SPIN_MAX << 4) && !done; i++) {
    asm volatile("{\n.reg .pred p;\nmbarrier.try_wait.parity.shared::cta.b64 p, [%1], 0;\nselp.u32 %0, 1, 0, p;\n}\n"
                 : "=r"(done) : "r"(b) : "memory");
  }
}
__device__ __forceinline__ void mbar_init(uint32_t b, int n) {
  asm volatile("mbarrier.init.shared::cta.b64 [%0], %1;" ::"r"(b), "r"(n) : "memory");
}
__device__ __forceinline__ void mbar_expect(uint32_t b, int bytes) {
  asm volatile("mbarrier.arrive.expect_tx.shared::cta.b64 _, [%0], %1;" ::"r"(b), "r"(bytes) : "memory");
}
__device__ __forceinline__ void nb_sync(int id, int n) { asm volatile("bar.sync %0, %1;" ::"r"(id), "r"(n) : "memory"); }
__device__ __forceinline__ void nb_arrive(int id, int n) { asm volatile("bar.arrive %0, %1;" ::"r"(id), "r"(n) : "memory"); }
#define ELECT "{\n.reg .pred p;\nelect.sync _|p, 0xffffffff;\n@p "
__device__ __forceinline__ void e_arrive(uint32_t b) {
  asm volatile(ELECT "mbarrier.arrive.shared::cta.b64 _, [%0];\n}\n" ::"r"(b) : "memory");
}
__device__ __forceinline__ void e_expect(uint32_t b, int bytes) {
  asm volatile(ELECT "mbarrier.arrive.expect_tx.shared::cta.b64 _, [%0], %1;\n}\n" ::"r"(b), "r"(bytes) : "memory");
}
__device__ __forceinline__ void e_tma2d(uint32_t dst, const CUtensorMap* m, uint32_t bar, int c0, int c1) {
  asm volatile(ELECT "cp.async.bulk.tensor.2d.shared::cluster.global.mbarrier::complete_tx::bytes [%0], [%1, {%3,%4}], [%2];\n}\n"
               ::"r"(dst), "l"(m), "r"(bar), "r"(c0), "r"(c1) : "memory");
}
__device__ __forceinline__ void e_tma3d(uint32_t dst, const CUtensorMap* m, uint32_t bar, int c0, int c1, int c2) {
  asm volatile(ELECT "cp.async.bulk.tensor.3d.shared::cluster.global.mbarrier::complete_tx::bytes [%0], [%1, {%3,%4,%5}], [%2];\n}\n"
               ::"r"(dst), "l"(m), "r"(bar), "r"(c0), "r"(c1), "r"(c2) : "memory");
}
__device__ __forceinline__ void e_tma4d(uint32_t dst, const CUtensorMap* m, uint32_t bar, int c0, int c3) {
  asm volatile(ELECT "cp.async.bulk.tensor.4d.shared::cluster.global.mbarrier::complete_tx::bytes [%0], [%1, {%3,%5,%5,%4}], [%2];\n}\n"
               ::"r"(dst), "l"(m), "r"(bar), "r"(c0), "r"(c3), "r"(0) : "memory");
}
__device__ __forceinline__ void e_bulk(uint32_t dst, const void* src, int bytes, uint32_t bar) {
  asm volatile(ELECT "cp.async.bulk.shared::cluster.global.mbarrier::complete_tx::bytes [%0], [%1], %2, [%3];\n}\n"
               ::"r"(dst), "l"(src), "r"(bytes), "r"(bar) : "memory");
}
__device__ __forceinline__ void e_prefetch(const void* p, int bytes) {
  asm volatile(ELECT "cp.async.bulk.prefetch.L2.global [%0], %1;\n}\n" ::"l"(p), "r"(bytes) : "memory");
}
__device__ __forceinline__ void e_store2d(const CUtensorMap* m, uint32_t src, int c0, int c1) {
  asm volatile(ELECT "cp.async.bulk.tensor.2d.global.shared::cta.bulk_group [%0, {%2,%3}], [%1];\n}\n"
               ::"l"(m), "r"(src), "r"(c0), "r"(c1) : "memory");
}
__host__ __device__ constexpr uint64_t mkdesc(uint32_t addr, uint32_t lbo, uint32_t sbo, int swz) {
  return (uint64_t)((addr & 0x3FFFF) >> 4) | ((uint64_t)(lbo >> 4) << 16) | ((uint64_t)(sbo >> 4) << 32) |
         ((uint64_t)swz << 62);
}
#define SPLIT() asm volatile("{\n.reg .pred p;\nsetp.eq.u32 p, %0, %1;\n@p exit;\n}\n" ::"r"(blockIdx.y), "n"(__LINE__) : "memory")
#define WG_FENCE() asm volatile("wgmma.fence.sync.aligned;" ::: "memory")
#define WG_COMMIT() asm volatile("wgmma.commit_group.sync.aligned;" ::: "memory")
#define WG_WAIT(n) asm volatile("wgmma.wait_group.sync.aligned " #n ";" ::: "memory")

__device__ __forceinline__ void mma(float& d0, float& d1, float& d2, float& d3, uint32_t a0, uint32_t a1, uint32_t a2,
                                    uint32_t a3, uint32_t b0, uint32_t b1) {
  asm volatile("mma.sync.aligned.m16n8k16.row.col.f32.bf16.bf16.f32 {%0,%1,%2,%3},{%4,%5,%6,%7},{%8,%9},{%0,%1,%2,%3};"
               : "+f"(d0), "+f"(d1), "+f"(d2), "+f"(d3)
               : "r"(a0), "r"(a1), "r"(a2), "r"(a3), "r"(b0), "r"(b1));
}
__device__ __forceinline__ void mmac(float (&d)[4], uint32_t a0, uint32_t a1, uint32_t a2, uint32_t a3, uint32_t b0,
                                     uint32_t b1, const float (&c)[4]) {
  asm volatile("mma.sync.aligned.m16n8k16.row.col.f32.bf16.bf16.f32 {%0,%1,%2,%3},{%4,%5,%6,%7},{%8,%9},{%10,%11,%12,%13};"
               : "=f"(d[0]), "=f"(d[1]), "=f"(d[2]), "=f"(d[3])
               : "r"(a0), "r"(a1), "r"(a2), "r"(a3), "r"(b0), "r"(b1), "f"(c[0]), "f"(c[1]), "f"(c[2]), "f"(c[3]));
}
__device__ __forceinline__ void mma_p(int p, float (&d)[4], uint32_t a0, uint32_t a1, uint32_t a2, uint32_t a3, uint32_t b0, uint32_t b1) {
  asm volatile("{\n.reg .pred q;\nsetp.ne.b32 q, %10, 0;\n"
               "@q mma.sync.aligned.m16n8k16.row.col.f32.bf16.bf16.f32 {%0,%1,%2,%3},{%4,%5,%6,%7},{%8,%9},{%0,%1,%2,%3};\n}\n"
               : "+f"(d[0]), "+f"(d[1]), "+f"(d[2]), "+f"(d[3])
               : "r"(a0), "r"(a1), "r"(a2), "r"(a3), "r"(b0), "r"(b1), "r"(p));
}
__device__ __forceinline__ void mmac_p(int p, float (&d)[4], uint32_t a0, uint32_t a1, uint32_t a2, uint32_t a3, uint32_t b0,
                                       uint32_t b1, const float (&c)[4]) {
  asm volatile("{\n.reg .pred q;\nsetp.ne.b32 q, %14, 0;\n"
               "@q mma.sync.aligned.m16n8k16.row.col.f32.bf16.bf16.f32 {%0,%1,%2,%3},{%4,%5,%6,%7},{%8,%9},{%10,%11,%12,%13};\n}\n"
               : "+f"(d[0]), "+f"(d[1]), "+f"(d[2]), "+f"(d[3])
               : "r"(a0), "r"(a1), "r"(a2), "r"(a3), "r"(b0), "r"(b1), "f"(c[0]), "f"(c[1]), "f"(c[2]), "f"(c[3]), "r"(p));
}
__device__ __forceinline__ void mma_h(float (&d)[4], const uint32_t (&a)[4], uint32_t b0, uint32_t b1) {
  asm volatile("mma.sync.aligned.m16n8k16.row.col.f32.f16.f16.f32 {%0,%1,%2,%3},{%4,%5,%6,%7},{%8,%9},{%0,%1,%2,%3};"
               : "+f"(d[0]), "+f"(d[1]), "+f"(d[2]), "+f"(d[3]) : "r"(a[0]), "r"(a[1]), "r"(a[2]), "r"(a[3]), "r"(b0), "r"(b1));
}
__device__ __forceinline__ void mma0(float& d0, float& d1, float& d2, float& d3, uint32_t a0, uint32_t a1, uint32_t a2,
                                     uint32_t a3, uint32_t b0, uint32_t b1) {
  asm volatile("mma.sync.aligned.m16n8k16.row.col.f32.bf16.bf16.f32 {%0,%1,%2,%3},{%4,%5,%6,%7},{%8,%9},{%10,%10,%10,%10};"
               : "=f"(d0), "=f"(d1), "=f"(d2), "=f"(d3)
               : "r"(a0), "r"(a1), "r"(a2), "r"(a3), "r"(b0), "r"(b1), "f"(0.f));
}
__device__ __forceinline__ uint32_t pack_bf(float lo, float hi) {
  uint32_t r;
  asm("cvt.rn.bf16x2.f32 %0, %1, %2;" : "=r"(r) : "f"(hi), "f"(lo));
  return r;
}
__device__ __forceinline__ float bf_lo(uint32_t w) { return __uint_as_float(w << 16); }
__device__ __forceinline__ float bf_hi(uint32_t w) { return __uint_as_float(w & 0xffff0000u); }
__device__ __forceinline__ float bf_round(float x) { return __bfloat162float(__float2bfloat16_rn(x)); }
__device__ __forceinline__ uint32_t bmax2(uint32_t a, uint32_t b) {
  uint32_t r; asm("max.bf16x2 %0, %1, %2;" : "=r"(r) : "r"(a), "r"(b)); return r;
}
__device__ __forceinline__ uint32_t bmin2(uint32_t a, uint32_t b) {
  uint32_t r; asm("min.bf16x2 %0, %1, %2;" : "=r"(r) : "r"(a), "r"(b)); return r;
}
__device__ __forceinline__ float ex2(float x) { float r; asm("ex2.approx.ftz.f32 %0, %1;" : "=f"(r) : "f"(x)); return r; }
__device__ __forceinline__ float rcp(float x) { float r; asm("rcp.approx.ftz.f32 %0, %1;" : "=f"(r) : "f"(x)); return r; }
__device__ __forceinline__ void ldsm4(uint32_t (&r)[4], uint32_t a) {
  asm volatile("ldmatrix.sync.aligned.m8n8.x4.shared.b16 {%0,%1,%2,%3}, [%4];"
               : "=r"(r[0]), "=r"(r[1]), "=r"(r[2]), "=r"(r[3]) : "r"(a) : "memory");
}
__device__ __forceinline__ void ldsm4t(uint32_t (&r)[4], uint32_t a) {
  asm volatile("ldmatrix.sync.aligned.m8n8.x4.trans.shared.b16 {%0,%1,%2,%3}, [%4];"
               : "=r"(r[0]), "=r"(r[1]), "=r"(r[2]), "=r"(r[3]) : "r"(a) : "memory");
}
__device__ __forceinline__ void stsm4(uint32_t a, uint32_t r0, uint32_t r1, uint32_t r2, uint32_t r3) {
  asm volatile("stmatrix.sync.aligned.m8n8.x4.shared.b16 [%0], {%1,%2,%3,%4};"
               ::"r"(a), "r"(r0), "r"(r1), "r"(r2), "r"(r3) : "memory");
}
__device__ __forceinline__ uint32_t lds32(uint32_t a) {
  uint32_t r; asm volatile("ld.shared.u32 %0, [%1];" : "=r"(r) : "r"(a) : "memory"); return r;
}
__device__ __forceinline__ uint32_t lds16(uint32_t a) {
  uint32_t r; asm volatile("{\n.reg .u16 h;\nld.shared.u16 h, [%1];\ncvt.u32.u16 %0, h;\n}\n" : "=r"(r) : "r"(a) : "memory"); return r;
}
__device__ __forceinline__ uint2 lds64(uint32_t a) {
  uint2 r; asm volatile("ld.shared.v2.u32 {%0,%1}, [%2];" : "=r"(r.x), "=r"(r.y) : "r"(a) : "memory"); return r;
}
__device__ __forceinline__ uint4 lds128(uint32_t a) {
  uint4 r;
  asm volatile("ld.shared.v4.u32 {%0,%1,%2,%3}, [%4];" : "=r"(r.x), "=r"(r.y), "=r"(r.z), "=r"(r.w) : "r"(a) : "memory");
  return r;
}
__device__ __forceinline__ void sts32(uint32_t a, uint32_t v) { asm volatile("st.shared.u32 [%0], %1;" ::"r"(a), "r"(v) : "memory"); }
__device__ __forceinline__ void sts16(uint32_t a, uint32_t v) {
  asm volatile("{\n.reg .u16 h;\ncvt.u16.u32 h, %1;\nst.shared.u16 [%0], h;\n}\n" ::"r"(a), "r"(v) : "memory");
}
__device__ __forceinline__ void sts64(uint32_t a, uint32_t x, uint32_t y) {
  asm volatile("st.shared.v2.u32 [%0], {%1,%2};" ::"r"(a), "r"(x), "r"(y) : "memory");
}
__device__ __forceinline__ void sts128(uint32_t a, uint32_t x, uint32_t y, uint32_t z, uint32_t w) {
  asm volatile("st.shared.v4.u32 [%0], {%1,%2,%3,%4};" ::"r"(a), "r"(x), "r"(y), "r"(z), "r"(w) : "memory");
}
__device__ __forceinline__ uint4 ld_x(const uint4* p) {
  uint4 r;
  asm volatile("{\n.reg .b128 t;\nld.relaxed.gpu.global.b128 t, [%4];\nmov.b128 {%0,%1,%2,%3}, t;\n}\n"
               : "=r"(r.x), "=r"(r.y), "=r"(r.z), "=r"(r.w) : "l"(p) : "memory");
  return r;
}
__device__ __forceinline__ uint32_t ld_x32(const uint32_t* p) {
  uint32_t r; asm volatile("ld.relaxed.gpu.global.u32 %0, [%1];" : "=r"(r) : "l"(p) : "memory"); return r;
}
__device__ __forceinline__ void st_x(uint4* p, uint32_t x, uint32_t y, uint32_t z, uint32_t w) {
  asm volatile("{\n.reg .b128 t;\nmov.b128 t, {%1,%2,%3,%4};\nst.relaxed.gpu.global.b128 [%0], t;\n}\n"
               ::"l"(p), "r"(x), "r"(y), "r"(z), "r"(w) : "memory");
}
__device__ __forceinline__ void st_x_p(int p, uint4* a, uint32_t x, uint32_t y, uint32_t z, uint32_t w) {
  asm volatile("{\n.reg .b128 t;\n.reg .pred q;\nsetp.ne.b32 q, %5, 0;\nmov.b128 t, {%1,%2,%3,%4};\n@q st.relaxed.gpu.global.b128 [%0], t;\n}\n"
               ::"l"(a), "r"(x), "r"(y), "r"(z), "r"(w), "r"(p) : "memory");
}
__device__ __forceinline__ void sts64_p(int p, uint32_t a, uint32_t x, uint32_t y) {
  asm volatile("{\n.reg .pred q;\nsetp.ne.b32 q, %3, 0;\n@q st.shared.v2.u32 [%0], {%1,%2};\n}\n" ::"r"(a), "r"(x), "r"(y), "r"(p) : "memory");
}
__device__ __forceinline__ void st_x32(uint32_t* p, uint32_t x) {
  asm volatile("st.relaxed.gpu.global.u32 [%0], %1;" ::"l"(p), "r"(x) : "memory");
}
__device__ __forceinline__ uint32_t nz(uint32_t w) { return max(w, 1u); }
__device__ __forceinline__ uint32_t fu(float x) { return __float_as_uint(x); }
__device__ __forceinline__ float uf(uint32_t x) { return __uint_as_float(x); }

__device__ __forceinline__ void wgmma_ss_n96(float (&d)[48], uint64_t da, uint64_t db, int sc) {
  asm volatile("{\n.reg .pred p;\nsetp.ne.b32 p, %50, 0;\n"
      "wgmma.mma_async.sync.aligned.m64n96k16.f32.bf16.bf16 "
      "{%0,%1,%2,%3,%4,%5,%6,%7,%8,%9,%10,%11,%12,%13,%14,%15,%16,%17,%18,%19,%20,%21,%22,%23,%24,%25,%26,%27,%28,%29,%30,%31,%32,%33,%34,%35,%36,%37,%38,%39,%40,%41,%42,%43,%44,%45,%46,%47}, "
      "%48, %49, p, 1, 1, 0, 1;\n}\n"
      : "+f"(d[0]), "+f"(d[1]), "+f"(d[2]), "+f"(d[3]), "+f"(d[4]), "+f"(d[5]), "+f"(d[6]), "+f"(d[7]),
        "+f"(d[8]), "+f"(d[9]), "+f"(d[10]), "+f"(d[11]), "+f"(d[12]), "+f"(d[13]), "+f"(d[14]), "+f"(d[15]),
        "+f"(d[16]), "+f"(d[17]), "+f"(d[18]), "+f"(d[19]), "+f"(d[20]), "+f"(d[21]), "+f"(d[22]), "+f"(d[23]),
        "+f"(d[24]), "+f"(d[25]), "+f"(d[26]), "+f"(d[27]), "+f"(d[28]), "+f"(d[29]), "+f"(d[30]), "+f"(d[31]),
        "+f"(d[32]), "+f"(d[33]), "+f"(d[34]), "+f"(d[35]), "+f"(d[36]), "+f"(d[37]), "+f"(d[38]), "+f"(d[39]),
        "+f"(d[40]), "+f"(d[41]), "+f"(d[42]), "+f"(d[43]), "+f"(d[44]), "+f"(d[45]), "+f"(d[46]), "+f"(d[47])
      : "l"(da), "l"(db), "r"(sc));
}

__device__ __forceinline__ void wgmma_ss_n128(float (&d)[64], uint64_t da, uint64_t db, int sc) {
  asm volatile("{\n.reg .pred p;\nsetp.ne.b32 p, %66, 0;\n"
      "wgmma.mma_async.sync.aligned.m64n128k16.f32.bf16.bf16 "
      "{%0,%1,%2,%3,%4,%5,%6,%7,%8,%9,%10,%11,%12,%13,%14,%15,%16,%17,%18,%19,%20,%21,%22,%23,%24,%25,%26,%27,%28,%29,%30,%31,%32,%33,%34,%35,%36,%37,%38,%39,%40,%41,%42,%43,%44,%45,%46,%47,%48,%49,%50,%51,%52,%53,%54,%55,%56,%57,%58,%59,%60,%61,%62,%63}, "
      "%64, %65, p, 1, 1, 0, 1;\n}\n"
      : "+f"(d[0]), "+f"(d[1]), "+f"(d[2]), "+f"(d[3]), "+f"(d[4]), "+f"(d[5]), "+f"(d[6]), "+f"(d[7]),
        "+f"(d[8]), "+f"(d[9]), "+f"(d[10]), "+f"(d[11]), "+f"(d[12]), "+f"(d[13]), "+f"(d[14]), "+f"(d[15]),
        "+f"(d[16]), "+f"(d[17]), "+f"(d[18]), "+f"(d[19]), "+f"(d[20]), "+f"(d[21]), "+f"(d[22]), "+f"(d[23]),
        "+f"(d[24]), "+f"(d[25]), "+f"(d[26]), "+f"(d[27]), "+f"(d[28]), "+f"(d[29]), "+f"(d[30]), "+f"(d[31]),
        "+f"(d[32]), "+f"(d[33]), "+f"(d[34]), "+f"(d[35]), "+f"(d[36]), "+f"(d[37]), "+f"(d[38]), "+f"(d[39]),
        "+f"(d[40]), "+f"(d[41]), "+f"(d[42]), "+f"(d[43]), "+f"(d[44]), "+f"(d[45]), "+f"(d[46]), "+f"(d[47]),
        "+f"(d[48]), "+f"(d[49]), "+f"(d[50]), "+f"(d[51]), "+f"(d[52]), "+f"(d[53]), "+f"(d[54]), "+f"(d[55]),
        "+f"(d[56]), "+f"(d[57]), "+f"(d[58]), "+f"(d[59]), "+f"(d[60]), "+f"(d[61]), "+f"(d[62]), "+f"(d[63])
      : "l"(da), "l"(db), "r"(sc));
}

__device__ __forceinline__ void wgmma_ss_n40(float (&d)[20], uint64_t da, uint64_t db, int sc) {
  asm volatile("{\n.reg .pred p;\nsetp.ne.b32 p, %22, 0;\n"
      "wgmma.mma_async.sync.aligned.m64n40k16.f32.bf16.bf16 "
      "{%0,%1,%2,%3,%4,%5,%6,%7,%8,%9,%10,%11,%12,%13,%14,%15,%16,%17,%18,%19}, "
      "%20, %21, p, 1, 1, 1, 1;\n}\n"
      : "+f"(d[0]), "+f"(d[1]), "+f"(d[2]), "+f"(d[3]), "+f"(d[4]), "+f"(d[5]), "+f"(d[6]), "+f"(d[7]),
        "+f"(d[8]), "+f"(d[9]), "+f"(d[10]), "+f"(d[11]), "+f"(d[12]), "+f"(d[13]), "+f"(d[14]), "+f"(d[15]),
        "+f"(d[16]), "+f"(d[17]), "+f"(d[18]), "+f"(d[19])
      : "l"(da), "l"(db), "r"(sc));
}

__device__ __forceinline__ void wgmma_rs_n8(float (&d)[4], const uint4& a, uint64_t db, int sc) {
  asm volatile("{\n.reg .pred p;\nsetp.ne.b32 p, %9, 0;\n"
      "wgmma.mma_async.sync.aligned.m64n8k16.f32.bf16.bf16 "
      "{%0,%1,%2,%3}, "
      "{%4,%5,%6,%7}, %8, p, 1, 1, 1;\n}\n"
      : "+f"(d[0]), "+f"(d[1]), "+f"(d[2]), "+f"(d[3])
      : "r"(a.x), "r"(a.y), "r"(a.z), "r"(a.w), "l"(db), "r"(sc));
}

__device__ __forceinline__ void wgmma_rs_n16(float (&d)[8], const uint4& a, uint64_t db, int sc) {
  asm volatile("{\n.reg .pred p;\nsetp.ne.b32 p, %13, 0;\n"
      "wgmma.mma_async.sync.aligned.m64n16k16.f32.bf16.bf16 "
      "{%0,%1,%2,%3,%4,%5,%6,%7}, "
      "{%8,%9,%10,%11}, %12, p, 1, 1, 1;\n}\n"
      : "+f"(d[0]), "+f"(d[1]), "+f"(d[2]), "+f"(d[3]), "+f"(d[4]), "+f"(d[5]), "+f"(d[6]), "+f"(d[7])
      : "r"(a.x), "r"(a.y), "r"(a.z), "r"(a.w), "l"(db), "r"(sc));
}

__device__ __forceinline__ void wgmma_rs_n24(float (&d)[12], const uint4& a, uint64_t db, int sc) {
  asm volatile("{\n.reg .pred p;\nsetp.ne.b32 p, %17, 0;\n"
      "wgmma.mma_async.sync.aligned.m64n24k16.f32.bf16.bf16 "
      "{%0,%1,%2,%3,%4,%5,%6,%7,%8,%9,%10,%11}, "
      "{%12,%13,%14,%15}, %16, p, 1, 1, 1;\n}\n"
      : "+f"(d[0]), "+f"(d[1]), "+f"(d[2]), "+f"(d[3]), "+f"(d[4]), "+f"(d[5]), "+f"(d[6]), "+f"(d[7]),
        "+f"(d[8]), "+f"(d[9]), "+f"(d[10]), "+f"(d[11])
      : "r"(a.x), "r"(a.y), "r"(a.z), "r"(a.w), "l"(db), "r"(sc));
}

struct Params {
  const __nv_bfloat16 *logA, *Aim, *Cre, *Cim, *logdt, *Dskip, *x, *wphi, *wo;
  __nv_bfloat16* out;
  uint4* xs;
  long long* ts;
};

__device__ __forceinline__ uint4 tr_row(const uint4 (&v)[8], int i) {
  uint32_t o[4];
#pragma unroll
  for (int m = 0; m < 4; m++) {
    const uint4 &ra = v[2 * m], &rb = v[2 * m + 1];
    const int k = i >> 1;
    const uint32_t xa = k == 0 ? ra.x : k == 1 ? ra.y : k == 2 ? ra.z : ra.w;
    const uint32_t xb = k == 0 ? rb.x : k == 1 ? rb.y : k == 2 ? rb.z : rb.w;
    o[m] = __byte_perm(xa, xb, (i & 1) ? 0x7632 : 0x5410);
  }
  return make_uint4(o[0], o[1], o[2], o[3]);
}

struct cpx { float r, i; };
__device__ __forceinline__ cpx csq(cpx a) { return {a.r * a.r - a.i * a.i, 2.f * (a.r * a.i)}; }
__device__ __forceinline__ cpx polar(float e, float t) {
  const float m = ex2(e);
  return {m * __cosf(t), m * __sinf(t)};
}

struct KgenRaw { unsigned short la, ai, cr, ci, ldt; };
__device__ __forceinline__ KgenRaw kgen_load(const Params& P, int d, int unit, int lane) {
  const int o = d * 128 + unit * 32 + lane;
  return {__ldg((const unsigned short*)P.logA + o), __ldg((const unsigned short*)P.Aim + o), __ldg((const unsigned short*)P.Cre + o),
          __ldg((const unsigned short*)P.Cim + o), __ldg((const unsigned short*)P.logdt + d)};
}
struct hmul { __half2 a, b; };
__device__ __forceinline__ hmul mk_mul(cpx w) {
  uint32_t b;
  asm("{\n.reg .f32 n;\nneg.ftz.f32 n, %1;\ncvt.rn.f16x2.f32 %0, %2, n;\n}\n" : "=r"(b) : "f"(w.i), "f"(w.r));
  return {__floats2half2_rn(w.r, w.i), *(const __half2*)&b};
}
__device__ __forceinline__ __half2 hcm(__half2 z, const hmul& w) { return __hfma2(__high2half2(z), w.b, __hmul2(__low2half2(z), w.a)); }
__device__ __forceinline__ uint32_t hu(__half2 v) { return *(const uint32_t*)&v; }

struct KgenAddr { uint32_t sa, lb, lm[4]; };
__device__ __forceinline__ KgenAddr kgen_addr(int lane, uint32_t buf) {
  KgenAddr a;
  a.sa = buf + (lane & 7) * 128 + ((((lane >> 3) ^ lane) & 7) << 4);
  const int q = lane >> 3;
  a.lb = buf + q * 128 + (((lane ^ q) & 7) << 4);
  a.lm[0] = buf + q * 128 + (q << 4);
  a.lm[1] = buf + q * 128 + ((1 ^ q) << 4);
  a.lm[2] = buf + q * 128 + (((2 + (lane & 1)) ^ q) << 4);
  a.lm[3] = buf + q * 128 + (((4 + (lane & 3)) ^ q) << 4);
  asm volatile("" : "+r"(a.sa), "+r"(a.lb), "+r"(a.lm[0]), "+r"(a.lm[1]), "+r"(a.lm[2]), "+r"(a.lm[3]));
  return a;
}
__device__ __forceinline__ void kgen_unit(const KgenRaw& r, const KgenAddr& ad, uint32_t zero, float (&k)[5][4], float& k2048, float& sc) {
  const float dt = bf_round(expf(bf_lo(r.ldt)));
  const float a2 = bf_round(ex2(bf_lo(r.la) * 1.4426950408889634f)) * (dt * -1.4426950408889634f);
  const float f = bf_lo(r.ai) * dt;
  const float r127 = f * 20.21267777267071f;
  const uint32_t ex = min(max(__reduce_max_sync(0xffffffffu, max(r.cr & 0x7fffu, r.ci & 0x7fffu)) >> 7, 1u), 253u);
  const float cs = uf((254u - ex) << 23);
  sc = 2.f * dt * uf(ex << 23);
  const cpx C = {bf_lo(r.cr) * cs, -bf_lo(r.ci) * cs};
  auto put = [&](const __half2 (&v)[8]) {
    stsm4(ad.sa, hu(v[0]), hu(v[1]), hu(v[2]), hu(v[3]));
    stsm4(ad.sa ^ 64, hu(v[4]), hu(v[5]), hu(v[6]), hu(v[7]));
    __syncwarp();
  };
  auto get = [&](uint32_t (&o)[2][4], uint32_t a) { ldsm4(o[0], a); ldsm4(o[1], (a ^ 64) + 512); };
  auto rot = [](uint32_t z) { return __byte_perm(z, z, 0x1032) ^ 0x8000u; };
  auto fmul = [](uint32_t z, uint32_t zi, uint32_t w) {
    const __half2 hw = *(const __half2*)&w;
    return hu(__hfma2(*(const __half2*)&zi, __high2half2(hw), __hmul2(*(const __half2*)&z, __low2half2(hw))));
  };
  uint32_t A[4][4];
  auto tile = [&](int j, const uint32_t (&B)[2][4]) {
    k[j][0] = k[j][1] = k[j][2] = k[j][3] = 0.f;
#pragma unroll
    for (int s = 0; s < 4; s++) mma_h(k[j], A[s], B[s >> 1][2 * (s & 1)], B[s >> 1][2 * (s & 1) + 1]);
  };
  auto after = [&](cpx v, uint32_t dep) { return cpx{uf(fu(v.r) ^ (dep & zero)), v.i}; };
  const cpx w1 = polar(a2, f), w127 = polar(a2 * 127.f, (r127 - rintf(r127)) * 6.283185307179586f);
  const cpx w2 = csq(w1), w4 = csq(w2);
  uint32_t T0[2][4], A0[2][4], T4[2][4], M[4][2][4];
  {
    __half2 t[8];
    const hmul m2 = mk_mul(w2), m4 = mk_mul(w4);
    t[0] = __floats2half2_rn(1.f, 0.f); t[1] = __floats2half2_rn(w1.r, w1.i); t[2] = m2.a; t[4] = m4.a;
    t[3] = hcm(t[1], m2); t[5] = hcm(t[1], m4); t[6] = hcm(t[2], m4); t[7] = hcm(t[3], m4);
    put(t); get(T0, ad.lb);
  }
  cpx w8 = csq(w4);
  w8.i = -w8.i;
  const cpx w16 = csq(w8), w32 = csq(w16), w64 = csq(w32);
  {
    const hmul m8 = mk_mul(w8), m16 = mk_mul(w16), m32 = mk_mul(w32);
    __half2 a[8];
    a[0] = __floats2half2_rn(C.r, C.i); a[1] = hcm(a[0], m8);
    a[2] = hcm(a[0], m16); a[3] = hcm(a[1], m16);
#pragma unroll
    for (int i = 0; i < 4; i++) a[4 + i] = hcm(a[i], m32);
    put(a); get(A0, ad.lb);
  }
  const cpx w127b = after(w127, T0[0][0]);
  const cpx w128 = {w127b.r * w1.r - w127b.i * w1.i, w127b.r * w1.i + w127b.i * w1.r};
  const cpx w256 = csq(w128), w512 = csq(w256);
  const hmul m128 = mk_mul(w128), m256 = mk_mul(w256), m512 = mk_mul(w512);
  {
    const hmul m254 = mk_mul(csq(w127b));
    const __half2 h127 = __floats2half2_rn(w127b.r, w127b.i);
    __half2 m[8];
    m[0] = __floats2half2_rn(w64.r, w64.i); m[1] = m128.a; m[2] = m256.a; m[3] = hcm(h127, m256);
    m[4] = m512.a; m[5] = hcm(h127, m512); m[6] = hcm(m[4], m254); m[7] = hcm(m[5], m254);
    put(m);
#pragma unroll
    for (int i = 0; i < 4; i++) get(M[i], ad.lm[i]);
  }
  const cpx w1024 = csq(after(w512, A0[0][0])), we = csq(w1024);
  {
    __half2 t[8];
    t[0] = __floats2half2_rn(w1024.r, w1024.i); t[1] = hcm(t[0], m128);
    t[2] = hcm(t[0], m256); t[3] = hcm(t[1], m256);
#pragma unroll
    for (int i = 0; i < 4; i++) t[4 + i] = hcm(t[i], m512);
    put(t); get(T4, ad.lb);
  }
  k2048 = (C.r * we.r + C.i * we.i) * sc;
#pragma unroll
  for (int i = 0; i < 8; i++) {
    const uint32_t z = A0[i >> 2][i & 3];
    A[i >> 1][2 * (i & 1)] = z;
    A[i >> 1][2 * (i & 1) + 1] = fmul(z, rot(z), M[0][i >> 2][i & 3]);
  }
  tile(0, T0);
#pragma unroll
  for (int i = 0; i < 8; i++) {
    const uint32_t z = T0[i >> 2][i & 3], zi = rot(z);
#pragma unroll
    for (int j = 1; j < 4; j++) M[j][i >> 2][i & 3] = fmul(z, zi, M[j][i >> 2][i & 3]);
  }
  tile(4, T4); tile(1, M[1]); tile(2, M[2]); tile(3, M[3]);
}

__device__ __forceinline__ void build_tables(uint32_t tb, int lane, float (&k)[5][4], float k2048) {
  const int g = lane >> 2, c = lane & 3;
  const uint32_t kc = tb + T_KC + 16;
  {
    const uint32_t a0 = kc + 16 * g + 4 * c, a2 = kc + 2 * (256 + 4 * g + c);
    const uint32_t a3 = kc + 2 * (384 + 2 * g + 64 * (c & 1) + (c >> 1)), a4 = kc + 2 * (512 + g + 32 * c);
#pragma unroll
    for (int r = 0; r < 2; r++) {
      sts32(a0 + 128 * r, pack_bf(k[0][2 * r], k[0][2 * r + 1]));
      sts32(a0 + 128 * r + 256, pack_bf(k[1][2 * r], k[1][2 * r + 1]));
      const uint32_t w2 = pack_bf(k[2][2 * r], k[2][2 * r + 1]);
      const uint32_t w3 = pack_bf(k[3][2 * r], k[3][2 * r + 1]);
      const uint32_t w4 = pack_bf(k[4][2 * r], k[4][2 * r + 1]);
      sts16(a2 + 64 * r, w2); sts16(a2 + 64 * r + 128, w2 >> 16);
      sts16(a3 + 32 * r, w3); sts16(a3 + 32 * r + 64, w3 >> 16);
      sts16(a4 + 16 * r, w4); sts16(a4 + 16 * r + 32, w4 >> 16);
    }
  }
  if (lane == 0) { sts16(kc + 2 * 640, pack_bf(k2048, 0.f)); sts32(kc - 4, 0); }
  __syncwarp();
  const uint32_t td = tb + T_D + 32;
#pragma unroll
  for (int hf = 0; hf < 2; hf++) {
    const uint2 v = lds64(kc + 256 * hf + 8 * lane);
    const uint32_t pv = lds32(kc + 256 * hf + 8 * lane - 4);
    sts128(td + 512 * hf + 16 * lane, __byte_perm(v.x, pv, 0x7610), __byte_perm(v.x, v.x, 0x1032), __byte_perm(v.y, v.x, 0x7610),
           __byte_perm(v.y, v.y, 0x1032));
  }
#pragma unroll
  for (int hf = 0; hf < 2; hf++) {
    const uint32_t v = lds32(kc + 512 + 128 * hf + 4 * lane), nx = lds32(kc + 516 + 128 * hf + 4 * lane);
    uint32_t w0 = __byte_perm(v, v, 0x1010);
    const uint32_t w1 = w0;
    if (hf == 0) { const uint32_t pv = lds32(kc + 508); if (lane == 0) w0 = __byte_perm(v, pv, 0x7610); }
    sts128(td + 1024 + 512 * hf + 16 * lane, w0, w1, __byte_perm(v, v, 0x1032), __byte_perm(nx, v, 0x7610));
  }
  {
    const uint32_t kk = lds16(kc + 2 * 384);
    const uint32_t w = lane < 3 ? (kk | (kk << 16)) : (lane == 3 ? (kk << 16) : 0u);
    if (lane < 24) sts32(td + 4 * (lane < 16 ? 512 + lane : lane - 24), w);
    const uint32_t lo_ = lds16(kc + 2 * 511), le_ = lds16(kc + 2 * 512);
    const uint32_t ja = tb + T_5 + (lane < 16 ? 4 * lane : 256 + 4 * lane);
    sts32(ja, lane == 16 ? (le_ << 16) : 0u);
    sts32(ja + 384, lane == 16 ? (lo_ << 16) : 0u);
    sts32(tb + (lane < 16 ? T_7 : T_9 - 64) + 4 * lane, 0u);
  }
#pragma unroll
  for (int s = 0; s < 2; s++) {
    const uint32_t b = kc + 2 * (s ? 512 : 384) + 8 * lane;
    const uint2 v = lds64(b);
    uint32_t em = lds16(b - 2), e0 = v.x;
    const uint32_t e4 = lds16(b + 8);
    if (lane == 0) { em = 0; e0 = 0; }
    sts64(tb + (s ? T_7 : T_3) + 64 + 8 * lane, __byte_perm(v.x, em, 0x5432), __byte_perm(v.y, v.x, 0x7632));
    sts64(tb + (s ? T_9 : T_5) + 64 + 8 * lane, __byte_perm(v.y, e0, 0x5410), __byte_perm(e4, v.y, 0x5410));
  }
  __syncwarp();
}

__device__ __forceinline__ uint32_t box2w(int lo, int n, int o) {
  return ((unsigned)(o - lo) < (unsigned)n ? 0x3F80u : 0u) | ((unsigned)(o + 1 - lo) < (unsigned)n ? 0x3F800000u : 0u);
}

__device__ __forceinline__ void conv_channel(uint32_t ub, uint32_t tb, int lane, uint4* ydst) {
  const int g = lane >> 2, c = lane & 3, x = g - 2 * c;
  const int mi = lane >> 3;
  const uint32_t qa = ub + U_PAD + 16 * (lane & 7) + ((mi == 0 || mi == 3) ? U_ODD : 0) - (mi == 0 ? 16 : 0);
  const uint32_t hb = ub + U_PAD + (mi & 1) * U_ODD + 16 * ((lane >> 4) + (lane & 7)) - 16;
  const uint32_t kv = lds16(tb + T_KC + 16 + 2 * 512);
  const int oh = c < 2 ? 8 + 2 * c : 2 * c - 8, og = c < 3 ? 2 * c : -10;
  uint32_t bx[4] = {box2w(g - 4, 9, 2 * c), box2w(g - 3, 7, 2 * c), box2w(g - 4, 9, oh), box2w(g - 3, 7, oh)};
  uint32_t by[4] = {box2w(g - 10, 5, 2 * c - 8), box2w(g - 5, 3, 2 * c - 8), box2w(g - 10, 5, og), box2w(g - 5, 3, og)};
  uint32_t lb0 = ((unsigned)(x + 5) < 2u ? kv : 0u) | ((unsigned)(x + 4) < 2u ? kv << 16 : 0u);
  uint32_t lb1 = ((unsigned)(x - 3) < 2u ? kv : 0u) | ((unsigned)(x - 4) < 2u ? kv << 16 : 0u);
  const int q0 = g - 1, q1 = c < 3 ? g : g - 2;
  uint32_t y0a = ub + U_PAD + (q0 & 1) * U_ODD + 16 * (q0 >> 1) + 4 * c;
  uint32_t y1a = ub + U_PAD + (q1 & 1) * U_ODD + 16 * (q1 >> 1) + 4 * c;
#pragma unroll
  for (int i = 0; i < 4; i++) asm volatile("" : "+r"(bx[i]), "+r"(by[i]));
  asm volatile("" : "+r"(lb0), "+r"(lb1), "+r"(y0a), "+r"(y1a));
  mbar_wait(BAR(MB_UFULL));
  mbar_spin(BAR(MB_EMPTY + 15));
  TS(36);
  float acc[16][4];
  {
    uint32_t z09[8], z07[8], zm9[8], zm7[8];
#pragma unroll
    for (int i = 0; i < 8; i++) {
      uint32_t h[4];
      ldsm4(h, hb + 128 * i);
      float y0, y1, y2, y3, w0, w1, w2, w3;
      mma0(y0, y1, y2, y3, bx[0], bx[1], bx[2], bx[3], h[2], c < 2 ? h[3] : h[1]);
      mma0(w0, w1, w2, w3, bx[0], bx[1], bx[2], bx[3], h[1], c < 2 ? h[2] : h[0]);
      z09[i] = pack_bf(y0, y1); z07[i] = pack_bf(y2, y3);
      zm9[i] = pack_bf(w0, w1); zm7[i] = pack_bf(w2, w3);
    }
  uint32_t f3[3][4][4];
  {
    const uint32_t fa = tb + T_7 + 4 * (16 + x);
#pragma unroll
    for (int tt = 0; tt < 3; tt++)
#pragma unroll
      for (int D = 0; D < 4; D++) {
        const uint32_t a = fa + (tt == 0 ? 316 : (tt == 1 ? 320 : 0)) + 64 * D;
        f3[tt][D][0] = lds32(a); f3[tt][D][1] = lds32(a + 32); f3[tt][D][2] = lds32(a - 32); f3[tt][D][3] = lds32(a);
      }
  }
    float a[4][2][4];
#pragma unroll
    for (int kap = 0; kap < 4; kap++)
#pragma unroll
      for (int sg = 0; sg < 2; sg++)
#pragma unroll
        for (int bk = 3; bk >= kap; bk--) {
          const uint32_t(&q0_)[4] = f3[sg ? 2 : 0][bk - kap];
          const uint32_t(&q1_)[4] = f3[sg ? 2 : 1][bk - kap];
          float(&a0)[4] = a[bk][0];
          float(&a1)[4] = a[bk][1];
          if (sg == 0 && kap == 0) {
            mma0(a0[0], a0[1], a0[2], a0[3], q0_[0], q0_[1], q0_[2], q0_[3], z09[0], z09[1]);
            mma0(a1[0], a1[1], a1[2], a1[3], q1_[0], q1_[1], q1_[2], q1_[3], zm9[0], zm9[1]);
          } else {
            mma(a0[0], a0[1], a0[2], a0[3], q0_[0], q0_[1], q0_[2], q0_[3], sg ? zm7[2 * kap] : z09[2 * kap], sg ? zm7[2 * kap + 1] : z09[2 * kap + 1]);
            mma(a1[0], a1[1], a1[2], a1[3], q1_[0], q1_[1], q1_[2], q1_[3], sg ? z07[2 * kap] : zm9[2 * kap], sg ? z07[2 * kap + 1] : zm9[2 * kap + 1]);
          }
        }
    SPLIT();
#pragma unroll
    for (int i = 0; i < 8; i++) {
      uint32_t h[4];
      ldsm4(h, qa + 128 * i);
      const float ci[4] = {a[i >> 1][0][2 * (i & 1)], a[i >> 1][0][2 * (i & 1) + 1], a[i >> 1][1][2 * (i & 1)], a[i >> 1][1][2 * (i & 1) + 1]};
      mmac(acc[8 + i], h[0], h[1], h[2], h[3], lb0, lb1, ci);
    }
  }
  TS(44);
  {
    uint2 a5[10], a3[10];
    const uint32_t aa = tb + T_5 + 4 * (8 + 2 * g - 2 * c);
#pragma unroll
    for (int m = 0; m < 10; m++) { a5[m] = lds64(aa + 32 * m); a3[m] = lds64(aa + 384 + 32 * m); }
    uint32_t x5[12][2], x3[12][2];
    auto ygen = [&](int kap) {
#pragma unroll
      for (int hh = 0; hh < 2; hh++) {
        float y0, y1, y2, y3;
        mma0(y0, y1, y2, y3, by[0], by[1], by[2], by[3], lds32(y0a + 128 * kap + 64 * hh), lds32(y1a + 128 * kap + 64 * hh));
        x5[kap][hh] = pack_bf(y0, y1);
        x3[kap][hh] = pack_bf(y2, y3);
      }
    };
    ygen(11); ygen(10); ygen(9); ygen(8);
#pragma unroll
    for (int kap = 11; kap >= 0; kap--) {
      if (kap >= 4) ygen(kap - 4);
#pragma unroll
      for (int sg = 0; sg < 2; sg++)
#pragma unroll
        for (int i = 4; i >= 0; i--) {
          const int be = kap + 4 + i;
          if (be <= 15) {
            const uint2 &hi = sg ? a3[2 * i + 1] : a5[2 * i + 1], &lo = sg ? a3[2 * i] : a5[2 * i];
            const uint32_t b0 = sg ? x3[kap][0] : x5[kap][0], b1 = sg ? x3[kap][1] : x5[kap][1];
            if (be < 8 && i == 0 && sg == 0) mma0(acc[be][0], acc[be][1], acc[be][2], acc[be][3], hi.x, hi.y, lo.x, lo.y, b0, b1);
            else mma(acc[be][0], acc[be][1], acc[be][2], acc[be][3], hi.x, hi.y, lo.x, lo.y, b0, b1);
          }
        }
    }
  }
  TS(45);
  {
    const uint32_t st = tb + T_ST + lane * 8;
#pragma unroll
    for (int be = 4; be < 12; be++) sts64(st + 256 * be, pack_bf(acc[be][0], acc[be][1]), pack_bf(acc[be][2], acc[be][3]));
    SPLIT();
    uint32_t F[66], qd[8][4];
    const uint32_t fa = tb + T_D + 32 + 4 * x;
#pragma unroll
    for (int i = 0; i < 32; i++) {
      const int s = 120 - (i >> 2) - 8 * (i & 3);
      uint32_t(&q)[4] = qd[i & 7];
      ldsm4(q, qa + 16 * s);
      const int m = 16 * (i & 3) + 2 * (i >> 2);
      F[m] = lds32(fa + 32 * m); F[m + 1] = lds32(fa + 32 * m + 32);
#pragma unroll
      for (int be = 15; be >= 12; be--) {
        const int de = 8 * be - s;
        float(&a)[4] = (be >= 14 && !(i & 1)) ? acc[be - 4] : acc[be];
        if (de >= 0 && be >= 14 && i == 2 * (15 - be)) mma0(a[0], a[1], a[2], a[3], q[0], q[1], q[2], q[3], F[2 * de + 1], F[2 * de]);
        else if (de >= 0) mma(a[0], a[1], a[2], a[3], q[0], q[1], q[2], q[3], F[2 * de + 1], F[2 * de]);
      }
    }
#pragma unroll
    for (int i = 0; i < 8; i++) acc[14 + (i >> 2)][i & 3] += acc[10 + (i >> 2)][i & 3];
    F[64] = lds32(fa + 32 * 64); F[65] = lds32(fa + 32 * 65);
    uint32_t qp = qa + 128 * 11, sta = st + 256 * 10;
    uint4* yd = ydst + 7 * 32;
#pragma unroll
    for (int i = 0; i < 6; i++) ldsm4(qd[i], qp - 16 * i);
    uint2 sv = lds64(sta + 256);
    float ci[4] = {bf_lo(sv.x), bf_hi(sv.x), bf_lo(sv.y), bf_hi(sv.y)};
    float T[5][4];
#pragma unroll
    for (int i = 0; i < 16; i++) T[i >> 2][i & 3] = acc[12 + (i >> 2)][i & 3];
    nb_sync(NB_YZ, 160);
    TS(46);
#pragma unroll 1
    for (int bp = 5; bp >= 0; bp--) {
      uint32_t held[2];
#pragma unroll
      for (int o = 1; o >= 0; o--) {
#pragma unroll
        for (int k = 4; k >= 1; k--) mmac(T[k], qd[0][0], qd[0][1], qd[0][2], qd[0][3], F[16 * k + 1], F[16 * k], T[k - 1]);
        mmac(T[0], qd[0][0], qd[0][1], qd[0][2], qd[0][3], F[1], F[0], ci);
        ldsm4(qd[6], qp - 16 * 6);
        ldsm4(qd[7], qp - 16 * 7);
        sv = lds64(sta);
#pragma unroll
        for (int i = 1; i < 8; i++) {
#pragma unroll
          for (int k = 3; k >= 0; k--)
            mma(T[k][0], T[k][1], T[k][2], T[k][3], qd[i][0], qd[i][1], qd[i][2], qd[i][3], F[16 * k + 2 * i + 1], F[16 * k + 2 * i]);
          if (i < 7) ldsm4(qd[i - 1], qp - 128 - 16 * (i - 1));
          if (i == 2) {
            const uint32_t w0 = pack_bf(T[4][0], T[4][1]), w1 = pack_bf(T[4][2], T[4][3]);
            if (o) { held[0] = w0; held[1] = w1; }
            else st_x(yd, nz(w0), w1, held[0], held[1]);
          }
          if (i == 4) {
            if (2 * bp + o <= 4) sv = make_uint2(0, 0);
            ci[0] = bf_lo(sv.x); ci[1] = bf_hi(sv.x); ci[2] = bf_lo(sv.y); ci[3] = bf_hi(sv.y);
          }
        }
        qp -= 128; sta -= 256;
      }
      yd -= 32;
      if (!(bp & 1)) nb_arrive(NB_Y + 1 + (bp >> 1), 160);
    }
#pragma unroll
    for (int B = 1; B >= 0; B--)
      st_x(ydst + B * 32, nz(pack_bf(T[2 * B][0], T[2 * B][1])), pack_bf(T[2 * B][2], T[2 * B][3]),
           pack_bf(T[2 * B + 1][0], T[2 * B + 1][1]), pack_bf(T[2 * B + 1][2], T[2 * B + 1][3]));
  }
}

__device__ __forceinline__ void dual_exp(const uint32_t* w, uint32_t* e) {
  const float L = 1.44268798828125f;
  uint32_t mx = bmax2(bmax2(w[0], w[1]), bmax2(w[2], w[3]));
  uint32_t mn = bmin2(bmin2(w[0], w[1]), bmin2(w[2], w[3]));
  mx = bmax2(mx, __shfl_xor_sync(0xffffffffu, mx, 1));
  mn = bmin2(mn, __shfl_xor_sync(0xffffffffu, mn, 1));
  mx = bmax2(mx, __shfl_xor_sync(0xffffffffu, mx, 2));
  mn = bmin2(mn, __shfl_xor_sync(0xffffffffu, mn, 2));
  const float mx0 = bf_lo(mx) * -L, mx1 = bf_hi(mx) * -L, mn0 = bf_lo(mn) * L, mn1 = bf_hi(mn) * L;
#pragma unroll
  for (int i = 0; i < 2; i++) {
    const float a0 = bf_lo(w[2 * i]), a1 = bf_hi(w[2 * i]), b0 = bf_lo(w[2 * i + 1]), b1 = bf_hi(w[2 * i + 1]);
    e[2 * i] = pack_bf(ex2(fmaf(a0, L, mx0)), ex2(fmaf(b0, L, mx0)));
    e[2 * i + 1] = pack_bf(ex2(fmaf(a1, L, mx1)), ex2(fmaf(b1, L, mx1)));
    e[4 + 2 * i] = pack_bf(ex2(fmaf(a0, -L, mn0)), ex2(fmaf(b0, -L, mn0)));
    e[5 + 2 * i] = pack_bf(ex2(fmaf(a1, -L, mn1)), ex2(fmaf(b1, -L, mn1)));
  }
}
__device__ __forceinline__ void normalise(uint32_t* e, const float (&s)[4]) {
  const uint32_t r = pack_bf(rcp(s[0]), rcp(s[2]));
  const __nv_bfloat162 rr = *(const __nv_bfloat162*)&r;
#pragma unroll
  for (int i = 0; i < 4; i++) {
    const __nv_bfloat162 v = __hmul2(*(const __nv_bfloat162*)&e[i], (i & 1) ? __high2bfloat162(rr) : __low2bfloat162(rr));
    e[i] = *(const uint32_t*)&v;
  }
}
__host__ __device__ constexpr uint64_t qdesc(uint32_t addr) { return mkdesc(addr, 128, 256, 0); }

__global__ void __launch_bounds__(NTHREADS, 1)
fused_kernel(const Params P, const __grid_constant__ CUtensorMap mx, const __grid_constant__ CUtensorMap mw,
             const __grid_constant__ CUtensorMap mo, const __grid_constant__ CUtensorMap mu,
             const __grid_constant__ CUtensorMap mout, const __grid_constant__ CUtensorMap mw4) {
  constexpr uint32_t sb = SB;
  const int tid = threadIdx.x, lane = tid & 31;
  const int warp = __shfl_sync(0xffffffffu, tid >> 5, 0);
  const int b = blockIdx.x, oct = b >> 3, i8 = b & 7;
  const int rt = (((oct & 4) ? ~oct : oct) & 3) * 2 + (i8 >> 2);
  const int hp = (oct >> 2) * 4 + (i8 & 3);

  const int wg = warp >> 2, w = warp & 3;
  const int d = b * 4 + ((tid >> 5) & 3);
  const KgenRaw raw = kgen_load(P, d, tid >> 7, lane);
  const unsigned short dsk = __ldg((const unsigned short*)P.Dskip + d);
  if (warp == 15) {
    asm volatile("prefetch.tensormap [%0];" ::"l"(&mu) : "memory");
    asm volatile("prefetch.tensormap [%0];" ::"l"(&mw) : "memory");
    asm volatile("prefetch.tensormap [%0];" ::"l"(&mx) : "memory");
    asm volatile("prefetch.tensormap [%0];" ::"l"(&mw4) : "memory");
  }
  if (warp == 12) {
    if (lane == 0) {
#pragma unroll
      for (int i = 0; i < 9; i++) mbar_init(BAR(i), 1);
      asm volatile("fence.mbarrier_init.release.cluster;" ::: "memory");
    }
    __syncwarp();
    if (lane < 9) mbar_expect(BAR(0) + 8 * lane, (lane == 5 || lane == 7) ? 40960 : ((lane == 0 || lane > 5) ? 16384 : 28672));
    __syncwarp();
    e_tma3d(sb + OFF_W, &mw, BAR(MB_FULL), hp * 32, 0, 0);
    e_tma2d(sb + OFF_X + 3 * 16384, &mx, BAR(MB_FULL), 0, rt * 256);
    nb_arrive(NB_PROD, 512);
  } else if (warp == 14) {
    e_prefetch(P.x + (size_t)(rt * 256 + hp * 8) * 512, 8192);
  } else if (warp == 13) {
    if (lane == 0) {
#pragma unroll
      for (int i = 9; i < 39; i++) mbar_init(BAR(i), i < MB_EMPTY ? 1 : 4);
      asm volatile("fence.mbarrier_init.release.cluster;" ::: "memory");
    }
    __syncwarp();
    if (lane < 13 && lane != 9) mbar_expect(BAR(MB_FULL + 8) + 8 * lane, lane < 8 ? 16384 : (lane == 8 ? 131072 : (lane == 10 ? 8192 : (lane == 11 ? 24576 : 32768))));
    nb_arrive(NB_PROD, 512);
  }
  const uint32_t tb = sb + OFF_T + w * T_CH;
  const uint32_t kp = wg == 2 ? sb + OFF_STG0 + 16384 + w * 1024 : ((tb + 127) & ~127u) + (wg == 3 ? 2 : wg) * 1536;
  const KgenAddr kad = kgen_addr(lane, kp);
  if ((warp >> 1) != 6) nb_sync(NB_PROD, 512);
  else nb_sync(NB_GATE + 1, 64);
  if (warp == 12) {
#pragma unroll 1
    for (int kb = 1; kb < 4; kb++) {
      if (kb == U_AT) e_tma4d(sb + OFF_STG0, &mu, BAR(MB_URAW), i8 * 64, oct * 2);
      e_tma3d(sb + OFF_W + kb * 12288, &mw, BAR(MB_FULL) + 8 * kb, hp * 32, kb * 64, 0);
      e_tma2d(sb + OFF_X + (kb < 2 ? kb + 3 : kb - 2) * 16384, &mx, BAR(MB_FULL) + 8 * kb, kb * 64, rt * 256);
    }
    e_tma4d(sb + OFF_W + 4 * 12288, &mw4, BAR(MB_FULL + 4), hp * 32, 4);
    e_tma2d(sb + OFF_X + 2 * 16384, &mx, BAR(MB_FULL + 4), 256, rt * 256);
    e_tma4d(sb + OFF_W + 6 * 12288, &mw4, BAR(MB_FULL + 6), hp * 32, 6);
    if (smem_u32(smem_raw) != SB) __trap();
    if (lane == 0) TS1(54);
  }
  float k[5][4], k2048, ksc;
  kgen_unit(raw, kad, blockIdx.y, k, k2048, ksc);
  TS(40 + wg);
  if ((fu(k[0][0]) & fu(k[1][0]) & fu(k[2][0]) & fu(k[3][0]) & fu(k[4][0])) == 0xffffffffu) sts32(kp, 0);
  if (wg) nb_arrive(0, 512);
  k2048 += __shfl_xor_sync(0xffffffffu, k2048, 16);
  k2048 += __shfl_xor_sync(0xffffffffu, k2048, 8);
  if (wg != 2) {
    uint32_t h[10];
#pragma unroll
    for (int j = 0; j < 10; j++) h[j] = hu(__floats2half2_rn(k[j >> 1][2 * (j & 1)], k[j >> 1][2 * (j & 1) + 1]));
    sts128(kp + lane * 16, h[0], h[1], h[2], h[3]);
    sts128(kp + 512 + lane * 16, h[4], h[5], h[6], h[7]);
    sts128(kp + 1024 + lane * 16, h[8], h[9], fu(k2048), fu(ksc));
  }
  if (wg == 0) { nb_arrive(NB_PREP, 512); nb_sync(0, 512); }
  else if (wg != 2) nb_arrive(NB_PREP, 512);
  else nb_sync(NB_PREP, 512);
  if (warp >= 12) {
    asm volatile("setmaxnreg.dec.sync.aligned.u32 32;");
    if (warp == 12) {
      if (X2_AT < 0) e_prefetch(P.x + (size_t)(rt * 256 + 128 + hp * 8) * 512, 8192);
      uint32_t slot = sb + OFF_X + 3 * 16384;
#pragma unroll 1
      for (int n = 0; n < 11; n++) {
        mbar_spin(BAR(MB_EMPTY) + 8 * n);
        const int m = n + 5;
        e_tma2d(slot, &mx, BAR(MB_FULL) + 8 * m, (m & 7) * 64, rt * 256 + (m >> 3) * 128);
        slot = slot == sb + OFF_X + 4 * 16384 ? sb + OFF_X : slot + 16384;
        if (n == X2_AT) e_prefetch(P.x + (size_t)(rt * 256 + 128 + hp * 8) * 512, 8192);
        if (n == 7) {
          e_prefetch(P.wo + (size_t)b * 2048, 4096);
          asm volatile("prefetch.tensormap [%0];" ::"l"(&mo) : "memory");
          asm volatile("prefetch.tensormap [%0];" ::"l"(&mout) : "memory");
        }
      }
#pragma unroll 1
      for (int i = 0; i < 8; i++) {
        mbar_wait(BAR(MB_EMPTY + 10) + 8 * ((0x54332222u >> (4 * i)) & 7));
        const int w0 = (0x54736210u >> (4 * i)) & 7;
        e_tma3d(sb + OFF_W + w0 * 16384, &mo, BAR(MB_WO), 0, w0 * 64, (hp & 3) * 2);
      }
    } else {
      if (warp == 15) {
        const uint4 v0 = __ldg((const uint4*)P.wphi + hp * 64 + lane), v1 = __ldg((const uint4*)P.wphi + hp * 64 + 32 + lane);
        sts128(sb + OFF_PHI + (lane & 1) * 256 + (lane >> 1) * 16, v0.x, v0.y, v0.z, v0.w);
        sts128(sb + OFF_PHI + 512 + (lane & 1) * 256 + (lane >> 1) * 16, v1.x, v1.y, v1.z, v1.w);
        const uint32_t one = (((lane >> 3) ^ (lane >> 4)) & 1) ? 0u : ((lane & 1) ? 0x3F800000u : 0x3F80u);
        const int q = (lane >> 1) & 3;
        sts128(sb + OFF_EYE + lane * 16, q == 0 ? one : 0u, q == 1 ? one : 0u, q == 2 ? one : 0u, q == 3 ? one : 0u);
        sts64(sb + OFF_ONE + lane * 8, 0x3F803F80u, 0x3F803F80u);
        asm volatile("fence.proxy.async.shared::cta;" ::: "memory");
        nb_arrive(NB_KREAD, 160);
      }
      uint32_t* cnt = (uint32_t*)(P.xs + X_CNT) + (warp == 13 ? i8 : (warp == 14 ? 8 + rt : 16 + oct)) * 32;
      const unsigned target = (ld_x32(cnt) & ~15u) + 16;
      if (warp != 14) {
        if (warp == 15) mbar_wait(BAR(MB_EMPTY + ZERO_STEP));
        uint4* pz = P.xs + (warp == 13 ? X_PART + (hp * 8 + rt) * 144 : X_Y + b * 1024) + lane;
#pragma unroll 1
        for (int i = (warp == 13 ? 144 : 1024) - lane; i > 0; i -= 32, pz += 32) st_x(pz, 0, 0, 0, 0);
      }
      if (warp == 15) __syncwarp();
      else nb_sync(warp == 13 ? NB_INIT : NB_ODONE, warp == 13 ? 160 : 288);
      if (lane == 0) asm volatile("red.release.gpu.global.add.u32 [%0], %1;" ::"l"(cnt), "r"(warp == 15 ? 2 : 1) : "memory");
      if (lane == 0) TS1(warp == 13 ? 50 : (warp == 14 ? 57 : 53));
      asm volatile("fence.proxy.async.shared::cta;" ::: "memory");
      if (warp == 13) cnt += ((lane & 1 ? b >> 4 : i8 ^ (lane & 4)) - i8) * 32;
#pragma unroll 1
      for (int i = 0; i < SPIN_MAX; i++) {
        unsigned v;
        asm volatile("ld.acquire.gpu.global.u32 %0, [%1];" : "=r"(v) : "l"(cnt) : "memory");
        if (__all_sync(0xffffffffu, (int)(v - target) >= 0)) break;
      }
      if (lane == 0) TS1(warp == 13 ? 51 : (warp == 14 ? 58 : 55));
      if (warp == 15) { nb_arrive(NB_YZ, 160); return; }
      asm volatile("fence.proxy.async.global;" ::: "memory");
      if (warp == 13) {
        mbar_wait(BAR(MB_EMPTY + 11));
        e_expect(BAR(MB_UFULL), 4 * U_CH);
        e_bulk(sb + OFF_U, P.xs + X_UT + b * (U_CH / 4), 4 * U_CH, BAR(MB_UFULL));
      } else {
        const uint4* src = P.xs + X_O + (rt * 4 + (hp >> 2)) * 4096;
        e_bulk(sb + OFF_X + 32768 + 57344, src + 3584, 8192, BAR(MB_OA));
        e_bulk(sb + OFF_X + 32768, src, 32768, BAR(MB_OC));
        e_bulk(sb + OFF_STG0, src + 3200, 6144, BAR(MB_OB));
        nb_sync(NB_BDONE, 288);
        asm volatile("fence.proxy.async.shared::cta;" ::: "memory");
        e_bulk(sb + OFF_U, src + 2048, 18432, BAR(MB_OB));
      }
    }
    return;
  }

  const int t = tid & 127;
  const int g = lane >> 2, c = lane & 3;
  if (wg == 1) {
    mbar_wait(BAR(MB_URAW));
    TS(48);
    uint4* dst = P.xs + X_UT + (i8 * 64 + g) * (U_CH / 16) + (w & 1) * (U_ODD / 16) + U_PAD / 16 + oct * 8 + (w >> 1) * 4 + c;
    const int ln = ((lane >> 1) & 3) + 4 * (lane & 1);
    uint32_t r[8][4];
#pragma unroll
    for (int i = 0; i < 8; i++) ldsm4t(r[i], sb + OFF_STG0 + w * 4096 + ((lane >> 3) * 8 + ln) * 128 + ((i ^ ln) << 4));
#pragma unroll
    for (int i = 0; i < 8; i++) dst[i * (U_CH / 2)] = make_uint4(r[i][0], r[i][1], r[i][2], r[i][3]);
    nb_arrive(NB_INIT, 160);
    if (lane == 0) mbar_arrive(BAR(MB_AUX));
  }
  {
    if (wg == 2) {
      asm volatile("setmaxnreg.inc.sync.aligned.u32 160;");
#pragma unroll
      for (int j = 0; j < 5; j++) { k[j][0] *= ksc; k[j][1] *= ksc; k[j][2] *= ksc; k[j][3] *= ksc; }
#pragma unroll 1
      for (int q = 0; q < 3; q++) {
        const uint32_t src = ((tb + 127) & ~127u) + q * 1536 + lane * 16;
        const uint4 v0 = lds128(src), v1 = lds128(src + 512), v2 = lds128(src + 1024);
        const uint32_t h[10] = {v0.x, v0.y, v0.z, v0.w, v1.x, v1.y, v1.z, v1.w, v2.x, v2.y};
#pragma unroll
        for (int j = 0; j < 10; j++) {
          const float2 f = __half22float2(*(const __half2*)&h[j]);
          k[j >> 1][2 * (j & 1)] = fmaf(f.x, uf(v2.w), k[j >> 1][2 * (j & 1)]);
          k[j >> 1][2 * (j & 1) + 1] = fmaf(f.y, uf(v2.w), k[j >> 1][2 * (j & 1) + 1]);
        }
        k2048 += uf(v2.z);
      }
#pragma unroll
      for (int o2 = 4; o2; o2 >>= 1) k2048 += __shfl_xor_sync(0xffffffffu, k2048, o2);
      if (lane == 0) k[0][0] += bf_lo(dsk);
      __syncwarp();
      TS(34);
      build_tables(tb, lane, k, k2048);
      TS(35);
      uint4* const g_y = P.xs + X_Y;
      conv_channel(sb + OFF_U + w * U_CH, tb, lane, g_y + (size_t)d * 256 + lane);
      nb_arrive(NB_BDONE, 288);
      nb_arrive(NB_Y, 160);
      TS(37);
      if (w == 0) TSDUMP(32);
      return;
    }
    if (wg == 1) {
      mbar_wait(BAR(MB_EMPTY + 4));
      mbar_spin(BAR(MB_EMPTY + 6));
    }
    TS(wg * 16 + 1);
  }

  float acc[2][48];
  {
    uint32_t fb = BAR(MB_FULL) + 64 * wg;
    uint32_t da = (uint32_t)mkdesc(sb + OFF_X, 16, 0, 0) + (wg ? 1024 : 3072), db = (uint32_t)mkdesc(sb + OFF_W, 4096, 0, 0);
    constexpr uint64_t ha = mkdesc(0, 0, 1024, 1), hb = mkdesc(0, 0, 512, 2);
    mbar_spin(fb);
    TS(wg * 16 + 2);
#pragma unroll 1
    for (int kb = 0; kb < 8; kb++) {
      WG_FENCE();
#pragma unroll
      for (int k = 0; k < 4; k++) {
        wgmma_ss_n96(acc[0], ha | (da + 2 * k), hb | (db + 64 * k), k ? 1 : kb);
        wgmma_ss_n96(acc[1], ha | (da + 2 * k + 512), hb | (db + 64 * k), k ? 1 : kb);
      }
      WG_COMMIT();
      if (kb < 7) mbar_spin(fb + 8);
      WG_WAIT(1);
      if (kb > 0) e_arrive(fb + 8 * (MB_EMPTY - MB_FULL - 1));
      fb += 8; db += 768;
      da = da == (uint32_t)mkdesc(sb + OFF_X + 65536, 16, 0, 0) ? da - 4096 : da + 1024;
    }
    if (wg == 0) nb_sync(NB_KREAD, 160);
    asm volatile("setmaxnreg.inc.sync.aligned.u32 160;");
    WG_WAIT(0);
    e_arrive(fb + 8 * (MB_EMPTY - MB_FULL - 1));
    SPLIT();
  }
  TS(wg * 16 + 3);

  constexpr uint32_t stg0 = sb + OFF_STG0, stg1 = sb + OFF_X + 32768;
  uint4* const g_part = P.xs + X_PART;
  uint4* const g_o = P.xs + X_O;
  constexpr uint32_t kvs = stg0;
  auto pack8 = [](const float* a) { return make_uint4(pack_bf(a[0], a[1]), pack_bf(a[2], a[3]), pack_bf(a[4], a[5]), pack_bf(a[6], a[7])); };
  auto feat = [&](const uint4 (&af)[4], float (&p)[4][8]) {
    WG_FENCE();
#pragma unroll
    for (int u = 0; u < 4; u++) wgmma_rs_n16(p[u], af[u], qdesc(sb + OFF_PHI + (u & 1) * 512), 0);
    WG_COMMIT();
  };
  auto packp = [](const float (&p)[4][8], uint32_t (&pw)[16]) {
#pragma unroll
    for (int i = 0; i < 16; i++) pw[i] = pack_bf(p[i >> 2][(i & 1) + 2 * (i & 2)], p[i >> 2][(i & 1) + 2 * (i & 2) + 2]);
  };
  auto contract = [&](float (&kc)[20], uint32_t stg, int acc_in) {
    WG_FENCE();
#pragma unroll
    for (int s = 0; s < 8; s++) wgmma_ss_n40(kc, qdesc(stg + s * SLAB), qdesc(stg + s * SLAB + 2048), s ? 1 : acc_in);
    WG_COMMIT();
    WG_WAIT(0);
  };
  uint32_t eq[32];
  {
    uint4 af[4], aq[4], vp[4];
    float p[4][8];
#pragma unroll
    for (int u = 0; u < 4; u++) af[u] = pack8(acc[u >> 1] + 16 + 8 * (u & 1));
    feat(af, p);
#pragma unroll
    for (int u = 0; u < 4; u++) { aq[u] = pack8(acc[u >> 1] + 8 * (u & 1)); vp[u] = pack8(acc[u >> 1] + 32 + 8 * (u & 1)); }
    WG_WAIT(0);
    uint32_t pw[16], ek[32];
    packp(p, pw);
#pragma unroll
    for (int u = 0; u < 4; u++) dual_exp(pw + 4 * u, ek + 8 * u);
    TS(wg * 16 + 12);
    mbar_spin(wg ? BAR(MB_EMPTY + 15) : BAR(MB_AUX));
    float rs[8][4];
    WG_FENCE();
#pragma unroll
    for (int i = 0; i < 8; i++) wgmma_rs_n8(rs[i], make_uint4(ek[4 * i], ek[4 * i + 1], ek[4 * i + 2], ek[4 * i + 3]), qdesc(sb + OFF_ONE), 0);
    WG_COMMIT();
    feat(aq, p);
    const uint32_t sl = (wg ? stg1 : stg0) + w * SLAB + lane * 16;
#pragma unroll
    for (int i = 0; i < 4; i++) stsm4(sl + (i >> 1) * 4 * SLAB + 2048 + (i & 1) * 512, vp[i].x, vp[i].y, vp[i].z, vp[i].w);
    sts128(sl + (lane >> 4) * (4 * SLAB - 256) + 3072, 0x3F803F80u, 0x3F803F80u, 0x3F803F80u, 0x3F803F80u);
    WG_WAIT(1);
#pragma unroll
    for (int i = 0; i < 8; i++) {
      normalise(ek + 4 * i, rs[i]);
      stsm4(sl + (i >> 2) * 4 * SLAB + (i & 3) * 512, ek[4 * i], ek[4 * i + 1], ek[4 * i + 2], ek[4 * i + 3]);
    }
    asm volatile("fence.proxy.async.shared::cta;" ::: "memory");
    TS(wg * 16 + 13);
    if (wg) {
      nb_arrive(NB_ST0, 256);
    } else {
      float kc[20];
      uint4* pp = g_part + (size_t)(hp * 8 + rt) * 144 + t;
      uint32_t* pz = (uint32_t*)(pp - t + 128) + w * 16 + c * 8 + g;
      asm volatile("" : "+l"(pp), "+l"(pz));
      nb_sync(NB_WG0, 128);
      contract(kc, stg0, 0);
      mbar_wait(BAR(MB_UFULL));
      TS(15);
      nb_sync(NB_ST0, 256);
      contract(kc, stg1, 1);
      TS(6);
      float kv[8];
#pragma unroll
      for (int i = 0; i < 8; i++) kv[i] = w & 2 ? kc[8 + i] : kc[i];
      st_x(pp, nz(pack_bf(kv[0], kv[1])), pack_bf(kv[2], kv[3]), pack_bf(kv[4], kv[5]), pack_bf(kv[6], kv[7]));
      if (c < 2) st_x32(pz, nz(fu(c ? kc[18] : kc[16])));
      TS(5);
    }
    SPLIT();
    WG_WAIT(0);
    packp(p, pw);
#pragma unroll
    for (int u = 0; u < 4; u++) dual_exp(pw + 4 * u, eq + 8 * u);
    SPLIT();
  }
  TS(wg * 16 + 4);
  if (wg == 1) {
    mbar_wait(BAR(MB_UFULL));
    const uint4* ps = g_part + (size_t)hp * 8 * 144 + t;
    const uint32_t* zs = (const uint32_t*)(g_part + (size_t)(hp * 8 + (lane >> 4) * 4) * 144 + 128) + w * 16 + (lane & 15);
    uint4 v[8];
    uint32_t zv[4];
#pragma unroll 1
    for (int it = 0; it < SPIN_MAX; it++) {
#pragma unroll
      for (int i = 0; i < 8; i++) v[i] = ld_x(ps + i * 144);
#pragma unroll
      for (int i = 0; i < 4; i++) zv[i] = ld_x32(zs + i * 576);
      uint32_t m = min(min(zv[0], zv[1]), min(zv[2], zv[3]));
#pragma unroll
      for (int i = 0; i < 8; i++) m = min(m, v[i].x);
      if (__all_sync(0xffffffffu, m != 0)) break;
    }
    float s[8];
    WG_FENCE();
#pragma unroll
    for (int r = 0; r < 8; r++) wgmma_rs_n16(s, v[r], qdesc(sb + OFF_EYE), r);
    WG_COMMIT();
    float zsum = (uf(zv[0]) + uf(zv[1])) + (uf(zv[2]) + uf(zv[3]));
    zsum += __shfl_xor_sync(0xffffffffu, zsum, 16);
    const uint32_t z1 = pack_bf(zsum, 1.f);
    if (lane < 16) sts128(kvs + w * 768 + 512 + lane * 16, z1, z1, z1, z1);
    WG_WAIT(0);
    stsm4(kvs + w * 768 + lane * 16, pack_bf(s[0], s[1]), pack_bf(s[2], s[3]), pack_bf(s[4], s[5]), pack_bf(s[6], s[7]));
    asm volatile("fence.proxy.async.shared::cta;" ::: "memory");
    TS(22);
  }
  nb_sync(NB_KV, 256);
  {
    float n[8][12];
    WG_FENCE();
#pragma unroll
    for (int i = 0; i < 8; i++) wgmma_rs_n24(n[i], make_uint4(eq[4 * i], eq[4 * i + 1], eq[4 * i + 2], eq[4 * i + 3]), qdesc(kvs + (i & 3) * 768), 0);
    WG_COMMIT();
    uint32_t* od = (uint32_t*)(g_o + (size_t)((rt * 4 + wg * 2) * 32 + hp * 2) * 128) + w * 64 + lane;
    WG_WAIT(0);
#pragma unroll
    for (int u = 0; u < 4; u++) {
      float(&np)[12] = n[2 * u];
      const float(&nm)[12] = n[2 * u + 1];
      const float q0 = np[9] * rcp(nm[9]), q1 = np[11] * rcp(nm[11]);
      const float r0 = rcp(fmaf(nm[8], q0, fmaf(np[9], 1e-6f, np[8]))), r1 = rcp(fmaf(nm[10], q1, fmaf(np[11], 1e-6f, np[10])));
#pragma unroll
      for (int i = 0; i < 8; i++) np[i] = fmaf(nm[i], (i & 2) ? q1 : q0, np[i]);
      uint32_t* o = od + (u >> 1) * 16384 + (u & 1) * 512;
      o[0] = pack_bf(np[0] * r0, np[1] * r0);
      o[32] = pack_bf(np[2] * r1, np[3] * r1);
      o[256] = pack_bf(np[4] * r0, np[5] * r0);
      o[288] = pack_bf(np[6] * r1, np[7] * r1);
      if (u == 1) SPLIT();
    }
  }
  TS(wg * 16 + 7);
  nb_arrive(NB_ODONE, 288);
  if (wg) {
    const uint4* src = P.xs + X_Y + (oct * 32 + c * 8) * 256 + (2 * w + (g >> 2)) * 32 + i8 * 4 + (g & 3);
    __nv_bfloat16* dst = P.out + (size_t)((2 * w + (g >> 2)) * 256 + i8 * 16 + (g & 3) * 2) * 1024 + 512 + oct * 32 + c * 8;
    nb_sync(NB_Y + w, 160);
    uint4 v[8];
#pragma unroll 1
    for (int it = 0; it < SPIN_MAX; it++) {
      uint32_t m = 0xffffffffu;
#pragma unroll
      for (int i = 0; i < 8; i++) v[i] = ld_x(src + i * 256);
#pragma unroll
      for (int i = 0; i < 8; i++) m = min(m, v[i].x);
      if (__all_sync(0xffffffffu, m != 0)) break;
    }
#pragma unroll
    for (int i = 0; i < 8; i++) *(uint4*)(dst + (size_t)((i >> 2) * 128 + ((i >> 1) & 1) * 8 + (i & 1)) * 1024) = tr_row(v, i);
    TS(31);
    GT(63);
    if (w == 0) TSDUMP(16);
    return;
  }
  mbar_wait(BAR(MB_WO));
  nb_sync(NB_BDONE, 288);
  TS(8);
  mbar_spin(BAR(MB_OA));
  TS(9);
  float oc[64];
  {
    constexpr uint64_t ha = mkdesc(0, 0, 128, 0), hb = mkdesc(0, 0, 1024, 1);
    constexpr uint32_t da0 = (uint32_t)mkdesc(stg1, 1024, 0, 0), db0 = (uint32_t)mkdesc(sb + OFF_W, 8192, 0, 0);
#pragma unroll 1
    for (int j = 0; j < 8; j++) {
      const int kb = (j + 7) & 7;
      if ((j & 3) == 1) mbar_spin(j == 1 ? BAR(MB_OC) : BAR(MB_OB));
      WG_FENCE();
#pragma unroll
      for (int k = 0; k < 4; k++) wgmma_ss_n128(oc, ha | (da0 + 512 * kb + 128 * k), hb | (db0 + 1024 * kb + 128 * k), k ? 1 : j);
      WG_COMMIT();
    }
    WG_WAIT(0);
  }
  TS(10);
  const uint32_t ot = ((sb + OFF_T + 1023) & ~1023u) + w * 4096;
#pragma unroll
  for (int hf = 0; hf < 2; hf++) {
#pragma unroll
    for (int i = 8 * hf; i < 8 * hf + 8; i += 2)
      stsm4(ot + hf * 2048 + (lane & 15) * 128 + (((i + (lane >> 4)) ^ lane) & 7) * 16, pack_bf(oc[4 * i], oc[4 * i + 1]),
            pack_bf(oc[4 * i + 2], oc[4 * i + 3]), pack_bf(oc[4 * i + 4], oc[4 * i + 5]), pack_bf(oc[4 * i + 6], oc[4 * i + 7]));
    asm volatile("fence.proxy.async.shared::cta;" ::: "memory");
    __syncwarp();
    e_store2d(&mout, ot + hf * 2048, (hp & 3) * 128 + hf * 64, (rt * 4 + (hp >> 2)) * 64 + w * 16);
  }
  asm volatile(ELECT "cp.async.bulk.commit_group;\n@p cp.async.bulk.wait_group.read 0;\n}\n" ::: "memory");
  TS(wg * 16 + 11);
  GT(61 + wg);
  if (w == 0) TSDUMP(0);
  if (w == 1) TSDUMP(48);
}

typedef CUresult (*EncodeFn)(CUtensorMap*, CUtensorMapDataType, cuuint32_t, void*, const cuuint64_t*, const cuuint64_t*,
                             const cuuint32_t*, const cuuint32_t*, CUtensorMapInterleave, CUtensorMapSwizzle,
                             CUtensorMapL2promotion, CUtensorMapFloatOOBfill);

}

extern "C" void kernel_launch(void* const* d_in, const int* in_sizes, int n_in, void* d_out, int out_size) {
  (void)in_sizes; (void)n_in; (void)out_size;
  void* fn = nullptr;
  cudaDriverEntryPointQueryResult qr;
  cudaGetDriverEntryPoint("cuTensorMapEncodeTiled", &fn, cudaEnableDefault, &qr);
  EncodeFn enc = (EncodeFn)fn;
  CUtensorMap mx, mw, mo, mu, mout, mw4;
  const cuuint32_t es[5] = {1, 1, 1, 1, 1};
  {
    cuuint64_t dims[2] = {512, 2048}, st[1] = {1024};
    cuuint32_t box[2] = {64, 128};
    enc(&mx, CU_TENSOR_MAP_DATA_TYPE_BFLOAT16, 2, d_in[0], dims, st, box, es, CU_TENSOR_MAP_INTERLEAVE_NONE,
        CU_TENSOR_MAP_SWIZZLE_128B, CU_TENSOR_MAP_L2_PROMOTION_L2_128B, CU_TENSOR_MAP_FLOAT_OOB_FILL_NONE);
  }
  {
    cuuint64_t dims[3] = {512, 512, 3}, st[2] = {3072, 1024};
    cuuint32_t box[3] = {32, 64, 3};
    enc(&mw, CU_TENSOR_MAP_DATA_TYPE_BFLOAT16, 3, d_in[1], dims, st, box, es, CU_TENSOR_MAP_INTERLEAVE_NONE,
        CU_TENSOR_MAP_SWIZZLE_64B, CU_TENSOR_MAP_L2_PROMOTION_L2_128B, CU_TENSOR_MAP_FLOAT_OOB_FILL_NONE);
  }
  {
    cuuint64_t dims[3] = {64, 512, 8}, st[2] = {1024, 128};
    cuuint32_t box[3] = {64, 64, 2};
    enc(&mo, CU_TENSOR_MAP_DATA_TYPE_BFLOAT16, 3, d_in[3], dims, st, box, es, CU_TENSOR_MAP_INTERLEAVE_NONE,
        CU_TENSOR_MAP_SWIZZLE_128B, CU_TENSOR_MAP_L2_PROMOTION_L2_128B, CU_TENSOR_MAP_FLOAT_OOB_FILL_NONE);
  }
  {
    cuuint64_t dims[4] = {512, 4, 16, 32}, st[3] = {16384, 1024, 65536};
    cuuint32_t box[4] = {64, 4, 16, 2};
    enc(&mu, CU_TENSOR_MAP_DATA_TYPE_BFLOAT16, 4, d_in[4], dims, st, box, es, CU_TENSOR_MAP_INTERLEAVE_NONE,
        CU_TENSOR_MAP_SWIZZLE_128B, CU_TENSOR_MAP_L2_PROMOTION_L2_128B, CU_TENSOR_MAP_FLOAT_OOB_FILL_NONE);
  }
  {
    cuuint64_t dims[2] = {1024, 2048}, st[1] = {2048};
    cuuint32_t box[2] = {64, 16};
    enc(&mout, CU_TENSOR_MAP_DATA_TYPE_BFLOAT16, 2, d_out, dims, st, box, es, CU_TENSOR_MAP_INTERLEAVE_NONE,
        CU_TENSOR_MAP_SWIZZLE_128B, CU_TENSOR_MAP_L2_PROMOTION_NONE, CU_TENSOR_MAP_FLOAT_OOB_FILL_NONE);
  }
  {
    cuuint64_t dims[4] = {512, 64, 3, 8}, st[3] = {3072, 1024, 64 * 3072};
    cuuint32_t box[4] = {32, 64, 3, 2};
    enc(&mw4, CU_TENSOR_MAP_DATA_TYPE_BFLOAT16, 4, d_in[1], dims, st, box, es, CU_TENSOR_MAP_INTERLEAVE_NONE,
        CU_TENSOR_MAP_SWIZZLE_64B, CU_TENSOR_MAP_L2_PROMOTION_L2_128B, CU_TENSOR_MAP_FLOAT_OOB_FILL_NONE);
  }
  Params P;
  P.x = (const __nv_bfloat16*)d_in[0];
  P.wphi = (const __nv_bfloat16*)d_in[2];
  P.wo = (const __nv_bfloat16*)d_in[3];
  P.logA = (const __nv_bfloat16*)d_in[5];
  P.Aim = (const __nv_bfloat16*)d_in[6];
  P.Cre = (const __nv_bfloat16*)d_in[7];
  P.Cim = (const __nv_bfloat16*)d_in[8];
  P.logdt = (const __nv_bfloat16*)d_in[9];
  P.Dskip = (const __nv_bfloat16*)d_in[10];
  P.out = (__nv_bfloat16*)d_out;
  cudaGetSymbolAddress((void**)&P.xs, g_x);
  P.ts = nullptr;
  cudaFuncSetAttribute(fused_kernel, cudaFuncAttributeMaxDynamicSharedMemorySize, SMEM_BYTES);
  fused_kernel<<<NCTA, NTHREADS, SMEM_BYTES>>>(P, mx, mw, mo, mu, mout, mw4);
}
```

```cpp
#include <cuda_runtime.h>
#include <cuda_bf16.h>
#include <cuda_fp16.h>
#include <cuda.h>
#include <stdint.h>

#define DBG_TS 0

namespace {

constexpr int NTHREADS = 512;
constexpr int NCTA = 128;
constexpr int OFF_W = 0;
constexpr int OFF_X = 98304;
constexpr int OFF_U = OFF_X + 65536;
constexpr int U_CH = 4416, U_ODD = 2240, U_PAD = 128;
constexpr int OFF_STG0 = OFF_U + 18432;
constexpr int SLAB = 3328;
constexpr int OFF_T = OFF_STG0 + 8 * SLAB;
constexpr int T_CH = 5216;
constexpr int T_D = 0;
constexpr int T_5 = 2144;
constexpr int T_3 = T_5 + 384;
constexpr int T_7 = T_5 + 1024;
constexpr int T_9 = T_7 + 320;
constexpr int T_KC = T_9 + 320;
constexpr int T_ST = T_5 - 1024;
constexpr int OFF_PHI = OFF_T + 4 * T_CH;
constexpr int OFF_EYE = OFF_PHI + 1024, OFF_ONE = OFF_EYE + 512;
constexpr int OFF_BAR = OFF_ONE + 256;
constexpr int SMEM_BYTES = OFF_BAR + 512 + 256 * DBG_TS;
constexpr uint32_t SB = 1024;
static_assert(T_KC + 2 * 656 <= T_CH, "table size");
static_assert(SMEM_BYTES <= 232448, "smem");
constexpr int MB_URAW = 0, MB_FULL = 1  , MB_WO = 17, MB_UFULL = 18, MB_O = 19  ,
              MB_EMPTY = 23  , MB_AUX = 39;
__host__ __device__ constexpr uint32_t BAR(int i) { return SB + OFF_BAR + 8 * i; }
constexpr int NB_WG0 = 1, NB_ODONE = 2, NB_ST0 = 3  , NB_KV = 5, NB_YZ = 6, NB_INIT = 7, NB_PREP = 8, NB_PROD = 9, NB_KREAD = 10, NB_BDONE = 11, NB_GATE = 12,
              NB_Y = 7  ;
#define X2_AT -1
#define GATE_B 0
#define NSPLIT 0
#define U_AT 2
#define ZERO_STEP 12
constexpr int SPIN_MAX = 1 << 16;

constexpr int X_CNT = 0;
constexpr int X_PART = 256;
constexpr int X_O = X_PART + 16 * 8 * 144;
constexpr int X_Y = X_O + 32 * 32 * 128;
constexpr int X_UT = X_Y + 512 * 8 * 32;
constexpr int X_SIZE = X_UT + 512 * (U_CH / 16);
__device__ __align__(128) uint4 g_x[X_SIZE];
extern __shared__ uint8_t smem_raw[];
#define TS(i) do {} while (0)
#define TS1(i) do {} while (0)
#define GT(i) do {} while (0)
#define TSDUMP(base) do {} while (0)

__device__ __forceinline__ uint32_t smem_u32(const void* p) { return (uint32_t)__cvta_generic_to_shared(p); }
__device__ __forceinline__ void mbar_arrive(uint32_t b) {
  asm volatile("mbarrier.arrive.shared::cta.b64 _, [%0];" ::"r"(b) : "memory");
}
__device__ __forceinline__ void mbar_wait(uint32_t b) {
  uint32_t done = 0;
#pragma unroll 1
  for (int i = 0; i < SPIN_MAX && !done; i++) {
    asm volatile("{\n.reg .pred p;\nmbarrier.try_wait.parity.shared::cta.b64 p, [%1], 0, 4000;\nselp.u32 %0, 1, 0, p;\n}\n"
                 : "=r"(done) : "r"(b) : "memory");
  }
}
__device__ __forceinline__ void mbar_spin(uint32_t b) {
  uint32_t done = 0;
#pragma unroll 1
  for (int i = 0; i < (SPIN_MAX << 4) && !done; i++) {
    asm volatile("{\n.reg .pred p;\nmbarrier.try_wait.parity.shared::cta.b64 p, [%1], 0;\nselp.u32 %0, 1, 0, p;\n}\n"
                 : "=r"(done) : "r"(b) : "memory");
  }
}
__device__ __forceinline__ void mbar_init(uint32_t b, int n) {
  asm volatile("mbarrier.init.shared::cta.b64 [%0], %1;" ::"r"(b), "r"(n) : "memory");
}
__device__ __forceinline__ void mbar_expect(uint32_t b, int bytes) {
  asm volatile("mbarrier.arrive.expect_tx.shared::cta.b64 _, [%0], %1;" ::"r"(b), "r"(bytes) : "memory");
}
__device__ __forceinline__ void nb_sync(int id, int n) { asm volatile("bar.sync %0, %1;" ::"r"(id), "r"(n) : "memory"); }
__device__ __forceinline__ void nb_arrive(int id, int n) { asm volatile("bar.arrive %0, %1;" ::"r"(id), "r"(n) : "memory"); }
#define ELECT "{\n.reg .pred p;\nelect.sync _|p, 0xffffffff;\n@p "
__device__ __forceinline__ void e_arrive(uint32_t b) {
  asm volatile(ELECT "mbarrier.arrive.shared::cta.b64 _, [%0];\n}\n" ::"r"(b) : "memory");
}
__device__ __forceinline__ void e_expect(uint32_t b, int bytes) {
  asm volatile(ELECT "mbarrier.arrive.expect_tx.shared::cta.b64 _, [%0], %1;\n}\n" ::"r"(b), "r"(bytes) : "memory");
}
__device__ __forceinline__ void e_tma2d(uint32_t dst, const CUtensorMap* m, uint32_t bar, int c0, int c1) {
  asm volatile(ELECT "cp.async.bulk.tensor.2d.shared::cluster.global.mbarrier::complete_tx::bytes [%0], [%1, {%3,%4}], [%2];\n}\n"
               ::"r"(dst), "l"(m), "r"(bar), "r"(c0), "r"(c1) : "memory");
}
__device__ __forceinline__ void e_tma3d(uint32_t dst, const CUtensorMap* m, uint32_t bar, int c0, int c1, int c2) {
  asm volatile(ELECT "cp.async.bulk.tensor.3d.shared::cluster.global.mbarrier::complete_tx::bytes [%0], [%1, {%3,%4,%5}], [%2];\n}\n"
               ::"r"(dst), "l"(m), "r"(bar), "r"(c0), "r"(c1), "r"(c2) : "memory");
}
__device__ __forceinline__ void e_tma4d(uint32_t dst, const CUtensorMap* m, uint32_t bar, int c0, int c3) {
  asm volatile(ELECT "cp.async.bulk.tensor.4d.shared::cluster.global.mbarrier::complete_tx::bytes [%0], [%1, {%3,%5,%5,%4}], [%2];\n}\n"
               ::"r"(dst), "l"(m), "r"(bar), "r"(c0), "r"(c3), "r"(0) : "memory");
}
__device__ __forceinline__ void e_bulk(uint32_t dst, const void* src, int bytes, uint32_t bar) {
  asm volatile(ELECT "cp.async.bulk.shared::cluster.global.mbarrier::complete_tx::bytes [%0], [%1], %2, [%3];\n}\n"
               ::"r"(dst), "l"(src), "r"(bytes), "r"(bar) : "memory");
}
__device__ __forceinline__ void e_prefetch(const void* p, int bytes) {
  asm volatile(ELECT "cp.async.bulk.prefetch.L2.global [%0], %1;\n}\n" ::"l"(p), "r"(bytes) : "memory");
}
__device__ __forceinline__ void e_store2d(const CUtensorMap* m, uint32_t src, int c0, int c1) {
  asm volatile(ELECT "cp.async.bulk.tensor.2d.global.shared::cta.bulk_group [%0, {%2,%3}], [%1];\n}\n"
               ::"l"(m), "r"(src), "r"(c0), "r"(c1) : "memory");
}
__host__ __device__ constexpr uint64_t mkdesc(uint32_t addr, uint32_t lbo, uint32_t sbo, int swz) {
  return (uint64_t)((addr & 0x3FFFF) >> 4) | ((uint64_t)(lbo >> 4) << 16) | ((uint64_t)(sbo >> 4) << 32) |
         ((uint64_t)swz << 62);
}
#define SPLIT() asm volatile("{\n.reg .pred p;\nsetp.eq.u32 p, %0, %1;\n@p exit;\n}\n" ::"r"(blockIdx.y), "n"(__LINE__) : "memory")
#define WG_FENCE() asm volatile("wgmma.fence.sync.aligned;" ::: "memory")
#define WG_COMMIT() asm volatile("wgmma.commit_group.sync.aligned;" ::: "memory")
#define WG_WAIT(n) asm volatile("wgmma.wait_group.sync.aligned " #n ";" ::: "memory")

__device__ __forceinline__ void mma(float& d0, float& d1, float& d2, float& d3, uint32_t a0, uint32_t a1, uint32_t a2,
                                    uint32_t a3, uint32_t b0, uint32_t b1) {
  asm volatile("mma.sync.aligned.m16n8k16.row.col.f32.bf16.bf16.f32 {%0,%1,%2,%3},{%4,%5,%6,%7},{%8,%9},{%0,%1,%2,%3};"
               : "+f"(d0), "+f"(d1), "+f"(d2), "+f"(d3)
               : "r"(a0), "r"(a1), "r"(a2), "r"(a3), "r"(b0), "r"(b1));
}
__device__ __forceinline__ void mmac(float (&d)[4], uint32_t a0, uint32_t a1, uint32_t a2, uint32_t a3, uint32_t b0,
                                     uint32_t b1, const float (&c)[4]) {
  asm volatile("mma.sync.aligned.m16n8k16.row.col.f32.bf16.bf16.f32 {%0,%1,%2,%3},{%4,%5,%6,%7},{%8,%9},{%10,%11,%12,%13};"
               : "=f"(d[0]), "=f"(d[1]), "=f"(d[2]), "=f"(d[3])
               : "r"(a0), "r"(a1), "r"(a2), "r"(a3), "r"(b0), "r"(b1), "f"(c[0]), "f"(c[1]), "f"(c[2]), "f"(c[3]));
}
__device__ __forceinline__ void mma_p(int p, float (&d)[4], uint32_t a0, uint32_t a1, uint32_t a2, uint32_t a3, uint32_t b0, uint32_t b1) {
  asm volatile("{\n.reg .pred q;\nsetp.ne.b32 q, %10, 0;\n"
               "@q mma.sync.aligned.m16n8k16.row.col.f32.bf16.bf16.f32 {%0,%1,%2,%3},{%4,%5,%6,%7},{%8,%9},{%0,%1,%2,%3};\n}\n"
               : "+f"(d[0]), "+f"(d[1]), "+f"(d[2]), "+f"(d[3])
               : "r"(a0), "r"(a1), "r"(a2), "r"(a3), "r"(b0), "r"(b1), "r"(p));
}
__device__ __forceinline__ void mmac_p(int p, float (&d)[4], uint32_t a0, uint32_t a1, uint32_t a2, uint32_t a3, uint32_t b0,
                                       uint32_t b1, const float (&c)[4]) {
  asm volatile("{\n.reg .pred q;\nsetp.ne.b32 q, %14, 0;\n"
               "@q mma.sync.aligned.m16n8k16.row.col.f32.bf16.bf16.f32 {%0,%1,%2,%3},{%4,%5,%6,%7},{%8,%9},{%10,%11,%12,%13};\n}\n"
               : "+f"(d[0]), "+f"(d[1]), "+f"(d[2]), "+f"(d[3])
               : "r"(a0), "r"(a1), "r"(a2), "r"(a3), "r"(b0), "r"(b1), "f"(c[0]), "f"(c[1]), "f"(c[2]), "f"(c[3]), "r"(p));
}
__device__ __forceinline__ void mma_h(float (&d)[4], const uint32_t (&a)[4], uint32_t b0, uint32_t b1) {
  asm volatile("mma.sync.aligned.m16n8k16.row.col.f32.f16.f16.f32 {%0,%1,%2,%3},{%4,%5,%6,%7},{%8,%9},{%0,%1,%2,%3};"
               : "+f"(d[0]), "+f"(d[1]), "+f"(d[2]), "+f"(d[3]) : "r"(a[0]), "r"(a[1]), "r"(a[2]), "r"(a[3]), "r"(b0), "r"(b1));
}
__device__ __forceinline__ void mma0(float& d0, float& d1, float& d2, float& d3, uint32_t a0, uint32_t a1, uint32_t a2,
                                     uint32_t a3, uint32_t b0, uint32_t b1) {
  asm volatile("mma.sync.aligned.m16n8k16.row.col.f32.bf16.bf16.f32 {%0,%1,%2,%3},{%4,%5,%6,%7},{%8,%9},{%10,%10,%10,%10};"
               : "=f"(d0), "=f"(d1), "=f"(d2), "=f"(d3)
               : "r"(a0), "r"(a1), "r"(a2), "r"(a3), "r"(b0), "r"(b1), "f"(0.f));
}
__device__ __forceinline__ uint32_t pack_bf(float lo, float hi) {
  uint32_t r;
  asm("cvt.rn.bf16x2.f32 %0, %1, %2;" : "=r"(r) : "f"(hi), "f"(lo));
  return r;
}
__device__ __forceinline__ float bf_lo(uint32_t w) { return __uint_as_float(w << 16); }
__device__ __forceinline__ float bf_hi(uint32_t w) { return __uint_as_float(w & 0xffff0000u); }
__device__ __forceinline__ float bf_round(float x) { return __bfloat162float(__float2bfloat16_rn(x)); }
__device__ __forceinline__ uint32_t bmax2(uint32_t a, uint32_t b) {
  uint32_t r; asm("max.bf16x2 %0, %1, %2;" : "=r"(r) : "r"(a), "r"(b)); return r;
}
__device__ __forceinline__ uint32_t bmin2(uint32_t a, uint32_t b) {
  uint32_t r; asm("min.bf16x2 %0, %1, %2;" : "=r"(r) : "r"(a), "r"(b)); return r;
}
__device__ __forceinline__ float ex2(float x) { float r; asm("ex2.approx.ftz.f32 %0, %1;" : "=f"(r) : "f"(x)); return r; }
__device__ __forceinline__ float rcp(float x) { float r; asm("rcp.approx.ftz.f32 %0, %1;" : "=f"(r) : "f"(x)); return r; }
__device__ __forceinline__ void ldsm4(uint32_t (&r)[4], uint32_t a) {
  asm volatile("ldmatrix.sync.aligned.m8n8.x4.shared.b16 {%0,%1,%2,%3}, [%4];"
               : "=r"(r[0]), "=r"(r[1]), "=r"(r[2]), "=r"(r[3]) : "r"(a) : "memory");
}
__device__ __forceinline__ void ldsm4t(uint32_t (&r)[4], uint32_t a) {
  asm volatile("ldmatrix.sync.aligned.m8n8.x4.trans.shared.b16 {%0,%1,%2,%3}, [%4];"
               : "=r"(r[0]), "=r"(r[1]), "=r"(r[2]), "=r"(r[3]) : "r"(a) : "memory");
}
__device__ __forceinline__ void stsm4(uint32_t a, uint32_t r0, uint32_t r1, uint32_t r2, uint32_t r3) {
  asm volatile("stmatrix.sync.aligned.m8n8.x4.shared.b16 [%0], {%1,%2,%3,%4};"
               ::"r"(a), "r"(r0), "r"(r1), "r"(r2), "r"(r3) : "memory");
}
__device__ __forceinline__ uint32_t lds32(uint32_t a) {
  uint32_t r; asm volatile("ld.shared.u32 %0, [%1];" : "=r"(r) : "r"(a) : "memory"); return r;
}
__device__ __forceinline__ uint32_t lds16(uint32_t a) {
  uint32_t r; asm volatile("{\n.reg .u16 h;\nld.shared.u16 h, [%1];\ncvt.u32.u16 %0, h;\n}\n" : "=r"(r) : "r"(a) : "memory"); return r;
}
__device__ __forceinline__ uint2 lds64(uint32_t a) {
  uint2 r; asm volatile("ld.shared.v2.u32 {%0,%1}, [%2];" : "=r"(r.x), "=r"(r.y) : "r"(a) : "memory"); return r;
}
__device__ __forceinline__ uint4 lds128(uint32_t a) {
  uint4 r;
  asm volatile("ld.shared.v4.u32 {%0,%1,%2,%3}, [%4];" : "=r"(r.x), "=r"(r.y), "=r"(r.z), "=r"(r.w) : "r"(a) : "memory");
  return r;
}
__device__ __forceinline__ void sts32(uint32_t a, uint32_t v) { asm volatile("st.shared.u32 [%0], %1;" ::"r"(a), "r"(v) : "memory"); }
__device__ __forceinline__ void sts16(uint32_t a, uint32_t v) {
  asm volatile("{\n.reg .u16 h;\ncvt.u16.u32 h, %1;\nst.shared.u16 [%0], h;\n}\n" ::"r"(a), "r"(v) : "memory");
}
__device__ __forceinline__ void sts64(uint32_t a, uint32_t x, uint32_t y) {
  asm volatile("st.shared.v2.u32 [%0], {%1,%2};" ::"r"(a), "r"(x), "r"(y) : "memory");
}
__device__ __forceinline__ void sts128(uint32_t a, uint32_t x, uint32_t y, uint32_t z, uint32_t w) {
  asm volatile("st.shared.v4.u32 [%0], {%1,%2,%3,%4};" ::"r"(a), "r"(x), "r"(y), "r"(z), "r"(w) : "memory");
}
__device__ __forceinline__ uint4 ld_x(const uint4* p) {
  uint4 r;
  asm volatile("{\n.reg .b128 t;\nld.relaxed.gpu.global.b128 t, [%4];\nmov.b128 {%0,%1,%2,%3}, t;\n}\n"
               : "=r"(r.x), "=r"(r.y), "=r"(r.z), "=r"(r.w) : "l"(p) : "memory");
  return r;
}
__device__ __forceinline__ uint32_t ld_x32(const uint32_t* p) {
  uint32_t r; asm volatile("ld.relaxed.gpu.global.u32 %0, [%1];" : "=r"(r) : "l"(p) : "memory"); return r;
}
__device__ __forceinline__ void st_x(uint4* p, uint32_t x, uint32_t y, uint32_t z, uint32_t w) {
  asm volatile("{\n.reg .b128 t;\nmov.b128 t, {%1,%2,%3,%4};\nst.relaxed.gpu.global.b128 [%0], t;\n}\n"
               ::"l"(p), "r"(x), "r"(y), "r"(z), "r"(w) : "memory");
}
__device__ __forceinline__ void st_x_p(int p, uint4* a, uint32_t x, uint32_t y, uint32_t z, uint32_t w) {
  asm volatile("{\n.reg .b128 t;\n.reg .pred q;\nsetp.ne.b32 q, %5, 0;\nmov.b128 t, {%1,%2,%3,%4};\n@q st.relaxed.gpu.global.b128 [%0], t;\n}\n"
               ::"l"(a), "r"(x), "r"(y), "r"(z), "r"(w), "r"(p) : "memory");
}
__device__ __forceinline__ void sts64_p(int p, uint32_t a, uint32_t x, uint32_t y) {
  asm volatile("{\n.reg .pred q;\nsetp.ne.b32 q, %3, 0;\n@q st.shared.v2.u32 [%0], {%1,%2};\n}\n" ::"r"(a), "r"(x), "r"(y), "r"(p) : "memory");
}
__device__ __forceinline__ void st_x32(uint32_t* p, uint32_t x) {
  asm volatile("st.relaxed.gpu.global.u32 [%0], %1;" ::"l"(p), "r"(x) : "memory");
}
__device__ __forceinline__ uint32_t nz(uint32_t w) { return max(w, 1u); }
__device__ __forceinline__ uint32_t fu(float x) { return __float_as_uint(x); }
__device__ __forceinline__ float uf(uint32_t x) { return __uint_as_float(x); }

__device__ __forceinline__ void wgmma_ss_n96(float (&d)[48], uint64_t da, uint64_t db, int sc) {
  asm volatile("{\n.reg .pred p;\nsetp.ne.b32 p, %50, 0;\n"
      "wgmma.mma_async.sync.aligned.m64n96k16.f32.bf16.bf16 "
      "{%0,%1,%2,%3,%4,%5,%6,%7,%8,%9,%10,%11,%12,%13,%14,%15,%16,%17,%18,%19,%20,%21,%22,%23,%24,%25,%26,%27,%28,%29,%30,%31,%32,%33,%34,%35,%36,%37,%38,%39,%40,%41,%42,%43,%44,%45,%46,%47}, "
      "%48, %49, p, 1, 1, 0, 1;\n}\n"
      : "+f"(d[0]), "+f"(d[1]), "+f"(d[2]), "+f"(d[3]), "+f"(d[4]), "+f"(d[5]), "+f"(d[6]), "+f"(d[7]),
        "+f"(d[8]), "+f"(d[9]), "+f"(d[10]), "+f"(d[11]), "+f"(d[12]), "+f"(d[13]), "+f"(d[14]), "+f"(d[15]),
        "+f"(d[16]), "+f"(d[17]), "+f"(d[18]), "+f"(d[19]), "+f"(d[20]), "+f"(d[21]), "+f"(d[22]), "+f"(d[23]),
        "+f"(d[24]), "+f"(d[25]), "+f"(d[26]), "+f"(d[27]), "+f"(d[28]), "+f"(d[29]), "+f"(d[30]), "+f"(d[31]),
        "+f"(d[32]), "+f"(d[33]), "+f"(d[34]), "+f"(d[35]), "+f"(d[36]), "+f"(d[37]), "+f"(d[38]), "+f"(d[39]),
        "+f"(d[40]), "+f"(d[41]), "+f"(d[42]), "+f"(d[43]), "+f"(d[44]), "+f"(d[45]), "+f"(d[46]), "+f"(d[47])
      : "l"(da), "l"(db), "r"(sc));
}

__device__ __forceinline__ void wgmma_ss_n128(float (&d)[64], uint64_t da, uint64_t db, int sc) {
  asm volatile("{\n.reg .pred p;\nsetp.ne.b32 p, %66, 0;\n"
      "wgmma.mma_async.sync.aligned.m64n128k16.f32.bf16.bf16 "
      "{%0,%1,%2,%3,%4,%5,%6,%7,%8,%9,%10,%11,%12,%13,%14,%15,%16,%17,%18,%19,%20,%21,%22,%23,%24,%25,%26,%27,%28,%29,%30,%31,%32,%33,%34,%35,%36,%37,%38,%39,%40,%41,%42,%43,%44,%45,%46,%47,%48,%49,%50,%51,%52,%53,%54,%55,%56,%57,%58,%59,%60,%61,%62,%63}, "
      "%64, %65, p, 1, 1, 0, 1;\n}\n"
      : "+f"(d[0]), "+f"(d[1]), "+f"(d[2]), "+f"(d[3]), "+f"(d[4]), "+f"(d[5]), "+f"(d[6]), "+f"(d[7]),
        "+f"(d[8]), "+f"(d[9]), "+f"(d[10]), "+f"(d[11]), "+f"(d[12]), "+f"(d[13]), "+f"(d[14]), "+f"(d[15]),
        "+f"(d[16]), "+f"(d[17]), "+f"(d[18]), "+f"(d[19]), "+f"(d[20]), "+f"(d[21]), "+f"(d[22]), "+f"(d[23]),
        "+f"(d[24]), "+f"(d[25]), "+f"(d[26]), "+f"(d[27]), "+f"(d[28]), "+f"(d[29]), "+f"(d[30]), "+f"(d[31]),
        "+f"(d[32]), "+f"(d[33]), "+f"(d[34]), "+f"(d[35]), "+f"(d[36]), "+f"(d[37]), "+f"(d[38]), "+f"(d[39]),
        "+f"(d[40]), "+f"(d[41]), "+f"(d[42]), "+f"(d[43]), "+f"(d[44]), "+f"(d[45]), "+f"(d[46]), "+f"(d[47]),
        "+f"(d[48]), "+f"(d[49]), "+f"(d[50]), "+f"(d[51]), "+f"(d[52]), "+f"(d[53]), "+f"(d[54]), "+f"(d[55]),
        "+f"(d[56]), "+f"(d[57]), "+f"(d[58]), "+f"(d[59]), "+f"(d[60]), "+f"(d[61]), "+f"(d[62]), "+f"(d[63])
      : "l"(da), "l"(db), "r"(sc));
}

__device__ __forceinline__ void wgmma_ss_n64(float (&d)[32], uint64_t da, uint64_t db, int sc) {
  asm volatile("{\n.reg .pred p;\nsetp.ne.b32 p, %34, 0;\n"
      "wgmma.mma_async.sync.aligned.m64n64k16.f32.bf16.bf16 "
      "{%0,%1,%2,%3,%4,%5,%6,%7,%8,%9,%10,%11,%12,%13,%14,%15,%16,%17,%18,%19,%20,%21,%22,%23,%24,%25,%26,%27,%28,%29,%30,%31}, "
      "%32, %33, p, 1, 1, 0, 1;\n}\n"
      : "+f"(d[0]), "+f"(d[1]), "+f"(d[2]), "+f"(d[3]), "+f"(d[4]), "+f"(d[5]), "+f"(d[6]), "+f"(d[7]),
        "+f"(d[8]), "+f"(d[9]), "+f"(d[10]), "+f"(d[11]), "+f"(d[12]), "+f"(d[13]), "+f"(d[14]), "+f"(d[15]),
        "+f"(d[16]), "+f"(d[17]), "+f"(d[18]), "+f"(d[19]), "+f"(d[20]), "+f"(d[21]), "+f"(d[22]), "+f"(d[23]),
        "+f"(d[24]), "+f"(d[25]), "+f"(d[26]), "+f"(d[27]), "+f"(d[28]), "+f"(d[29]), "+f"(d[30]), "+f"(d[31])
      : "l"(da), "l"(db), "r"(sc));
}

__device__ __forceinline__ void wgmma_ss_n40(float (&d)[20], uint64_t da, uint64_t db, int sc) {
  asm volatile("{\n.reg .pred p;\nsetp.ne.b32 p, %22, 0;\n"
      "wgmma.mma_async.sync.aligned.m64n40k16.f32.bf16.bf16 "
      "{%0,%1,%2,%3,%4,%5,%6,%7,%8,%9,%10,%11,%12,%13,%14,%15,%16,%17,%18,%19}, "
      "%20, %21, p, 1, 1, 1, 1;\n}\n"
      : "+f"(d[0]), "+f"(d[1]), "+f"(d[2]), "+f"(d[3]), "+f"(d[4]), "+f"(d[5]), "+f"(d[6]), "+f"(d[7]),
        "+f"(d[8]), "+f"(d[9]), "+f"(d[10]), "+f"(d[11]), "+f"(d[12]), "+f"(d[13]), "+f"(d[14]), "+f"(d[15]),
        "+f"(d[16]), "+f"(d[17]), "+f"(d[18]), "+f"(d[19])
      : "l"(da), "l"(db), "r"(sc));
}

__device__ __forceinline__ void wgmma_rs_n8(float (&d)[4], const uint4& a, uint64_t db, int sc) {
  asm volatile("{\n.reg .pred p;\nsetp.ne.b32 p, %9, 0;\n"
      "wgmma.mma_async.sync.aligned.m64n8k16.f32.bf16.bf16 "
      "{%0,%1,%2,%3}, "
      "{%4,%5,%6,%7}, %8, p, 1, 1, 1;\n}\n"
      : "+f"(d[0]), "+f"(d[1]), "+f"(d[2]), "+f"(d[3])
      : "r"(a.x), "r"(a.y), "r"(a.z), "r"(a.w), "l"(db), "r"(sc));
}

__device__ __forceinline__ void wgmma_rs_n16(float (&d)[8], const uint4& a, uint64_t db, int sc) {
  asm volatile("{\n.reg .pred p;\nsetp.ne.b32 p, %13, 0;\n"
      "wgmma.mma_async.sync.aligned.m64n16k16.f32.bf16.bf16 "
      "{%0,%1,%2,%3,%4,%5,%6,%7}, "
      "{%8,%9,%10,%11}, %12, p, 1, 1, 1;\n}\n"
      : "+f"(d[0]), "+f"(d[1]), "+f"(d[2]), "+f"(d[3]), "+f"(d[4]), "+f"(d[5]), "+f"(d[6]), "+f"(d[7])
      : "r"(a.x), "r"(a.y), "r"(a.z), "r"(a.w), "l"(db), "r"(sc));
}

__device__ __forceinline__ void wgmma_rs_n24(float (&d)[12], const uint4& a, uint64_t db, int sc) {
  asm volatile("{\n.reg .pred p;\nsetp.ne.b32 p, %17, 0;\n"
      "wgmma.mma_async.sync.aligned.m64n24k16.f32.bf16.bf16 "
      "{%0,%1,%2,%3,%4,%5,%6,%7,%8,%9,%10,%11}, "
      "{%12,%13,%14,%15}, %16, p, 1, 1, 1;\n}\n"
      : "+f"(d[0]), "+f"(d[1]), "+f"(d[2]), "+f"(d[3]), "+f"(d[4]), "+f"(d[5]), "+f"(d[6]), "+f"(d[7]),
        "+f"(d[8]), "+f"(d[9]), "+f"(d[10]), "+f"(d[11])
      : "r"(a.x), "r"(a.y), "r"(a.z), "r"(a.w), "l"(db), "r"(sc));
}

struct Params {
  const __nv_bfloat16 *logA, *Aim, *Cre, *Cim, *logdt, *Dskip, *x, *wphi, *wo;
  __nv_bfloat16* out;
  uint4* xs;
  long long* ts;
};

__device__ __forceinline__ uint4 tr_row(const uint4 (&v)[8], int i) {
  uint32_t o[4];
#pragma unroll
  for (int m = 0; m < 4; m++) {
    const uint4 &ra = v[2 * m], &rb = v[2 * m + 1];
    const int k = i >> 1;
    const uint32_t xa = k == 0 ? ra.x : k == 1 ? ra.y : k == 2 ? ra.z : ra.w;
    const uint32_t xb = k == 0 ? rb.x : k == 1 ? rb.y : k == 2 ? rb.z : rb.w;
    o[m] = __byte_perm(xa, xb, (i & 1) ? 0x7632 : 0x5410);
  }
  return make_uint4(o[0], o[1], o[2], o[3]);
}

struct cpx { float r, i; };
__device__ __forceinline__ cpx csq(cpx a) { return {a.r * a.r - a.i * a.i, 2.f * (a.r * a.i)}; }
__device__ __forceinline__ cpx polar(float e, float t) {
  const float m = ex2(e);
  return {m * __cosf(t), m * __sinf(t)};
}

struct KgenRaw { unsigned short la, ai, cr, ci, ldt; };
__device__ __forceinline__ KgenRaw kgen_load(const Params& P, int d, int unit, int lane) {
  const int o = d * 128 + unit * 32 + lane;
  return {__ldg((const unsigned short*)P.logA + o), __ldg((const unsigned short*)P.Aim + o), __ldg((const unsigned short*)P.Cre + o),
          __ldg((const unsigned short*)P.Cim + o), __ldg((const unsigned short*)P.logdt + d)};
}
struct hmul { __half2 a, b; };
__device__ __forceinline__ hmul mk_mul(cpx w) {
  uint32_t b;
  asm("{\n.reg .f32 n;\nneg.ftz.f32 n, %1;\ncvt.rn.f16x2.f32 %0, %2, n;\n}\n" : "=r"(b) : "f"(w.i), "f"(w.r));
  return {__floats2half2_rn(w.r, w.i), *(const __half2*)&b};
}
__device__ __forceinline__ __half2 hcm(__half2 z, const hmul& w) { return __hfma2(__high2half2(z), w.b, __hmul2(__low2half2(z), w.a)); }
__device__ __forceinline__ uint32_t hu(__half2 v) { return *(const uint32_t*)&v; }

struct KgenAddr { uint32_t sa, lb, lm[4]; };
__device__ __forceinline__ KgenAddr kgen_addr(int lane, uint32_t buf) {
  KgenAddr a;
  a.sa = buf + (lane & 7) * 128 + ((((lane >> 3) ^ lane) & 7) << 4);
  const int q = lane >> 3;
  a.lb = buf + q * 128 + (((lane ^ q) & 7) << 4);
  a.lm[0] = buf + q * 128 + (q << 4);
  a.lm[1] = buf + q * 128 + ((1 ^ q) << 4);
  a.lm[2] = buf + q * 128 + (((2 + (lane & 1)) ^ q) << 4);
  a.lm[3] = buf + q * 128 + (((4 + (lane & 3)) ^ q) << 4);
  asm volatile("" : "+r"(a.sa), "+r"(a.lb), "+r"(a.lm[0]), "+r"(a.lm[1]), "+r"(a.lm[2]), "+r"(a.lm[3]));
  return a;
}
__device__ __forceinline__ void kgen_unit(const KgenRaw& r, const KgenAddr& ad, uint32_t zero, float (&k)[5][4], float& k2048, float& sc) {
  const float dt = bf_round(expf(bf_lo(r.ldt)));
  const float a2 = bf_round(ex2(bf_lo(r.la) * 1.4426950408889634f)) * (dt * -1.4426950408889634f);
  const float f = bf_lo(r.ai) * dt;
  const float r127 = f * 20.21267777267071f;
  const uint32_t ex = min(max(__reduce_max_sync(0xffffffffu, max(r.cr & 0x7fffu, r.ci & 0x7fffu)) >> 7, 1u), 253u);
  const float cs = uf((254u - ex) << 23);
  sc = 2.f * dt * uf(ex << 23);
  const cpx C = {bf_lo(r.cr) * cs, -bf_lo(r.ci) * cs};
  auto put = [&](const __half2 (&v)[8]) {
    stsm4(ad.sa, hu(v[0]), hu(v[1]), hu(v[2]), hu(v[3]));
    stsm4(ad.sa ^ 64, hu(v[4]), hu(v[5]), hu(v[6]), hu(v[7]));
    __syncwarp();
  };
  auto get = [&](uint32_t (&o)[2][4], uint32_t a) { ldsm4(o[0], a); ldsm4(o[1], (a ^ 64) + 512); };
  auto rot = [](uint32_t z) { return __byte_perm(z, z, 0x1032) ^ 0x8000u; };
  auto fmul = [](uint32_t z, uint32_t zi, uint32_t w) {
    const __half2 hw = *(const __half2*)&w;
    return hu(__hfma2(*(const __half2*)&zi, __high2half2(hw), __hmul2(*(const __half2*)&z, __low2half2(hw))));
  };
  uint32_t A[4][4];
  auto tile = [&](int j, const uint32_t (&B)[2][4]) {
    k[j][0] = k[j][1] = k[j][2] = k[j][3] = 0.f;
#pragma unroll
    for (int s = 0; s < 4; s++) mma_h(k[j], A[s], B[s >> 1][2 * (s & 1)], B[s >> 1][2 * (s & 1) + 1]);
  };
  auto after = [&](cpx v, uint32_t dep) { return cpx{uf(fu(v.r) ^ (dep & zero)), v.i}; };
  const cpx w1 = polar(a2, f), w127 = polar(a2 * 127.f, (r127 - rintf(r127)) * 6.283185307179586f);
  const cpx w2 = csq(w1), w4 = csq(w2);
  uint32_t T0[2][4], A0[2][4], T4[2][4], M[4][2][4];
  {
    __half2 t[8];
    const hmul m2 = mk_mul(w2), m4 = mk_mul(w4);
    t[0] = __floats2half2_rn(1.f, 0.f); t[1] = __floats2half2_rn(w1.r, w1.i); t[2] = m2.a; t[4] = m4.a;
    t[3] = hcm(t[1], m2); t[5] = hcm(t[1], m4); t[6] = hcm(t[2], m4); t[7] = hcm(t[3], m4);
    put(t); get(T0, ad.lb);
  }
  cpx w8 = csq(w4);
  w8.i = -w8.i;
  const cpx w16 = csq(w8), w32 = csq(w16), w64 = csq(w32);
  {
    const hmul m8 = mk_mul(w8), m16 = mk_mul(w16), m32 = mk_mul(w32);
    __half2 a[8];
    a[0] = __floats2half2_rn(C.r, C.i); a[1] = hcm(a[0], m8);
    a[2] = hcm(a[0], m16); a[3] = hcm(a[1], m16);
#pragma unroll
    for (int i = 0; i < 4; i++) a[4 + i] = hcm(a[i], m32);
    put(a); get(A0, ad.lb);
  }
  const cpx w127b = after(w127, T0[0][0]);
  const cpx w128 = {w127b.r * w1.r - w127b.i * w1.i, w127b.r * w1.i + w127b.i * w1.r};
  const cpx w256 = csq(w128), w512 = csq(w256);
  const hmul m128 = mk_mul(w128), m256 = mk_mul(w256), m512 = mk_mul(w512);
  {
    const hmul m254 = mk_mul(csq(w127b));
    const __half2 h127 = __floats2half2_rn(w127b.r, w127b.i);
    __half2 m[8];
    m[0] = __floats2half2_rn(w64.r, w64.i); m[1] = m128.a; m[2] = m256.a; m[3] = hcm(h127, m256);
    m[4] = m512.a; m[5] = hcm(h127, m512); m[6] = hcm(m[4], m254); m[7] = hcm(m[5], m254);
    put(m);
#pragma unroll
    for (int i = 0; i < 4; i++) get(M[i], ad.lm[i]);
  }
  const cpx w1024 = csq(after(w512, A0[0][0])), we = csq(w1024);
  {
    __half2 t[8];
    t[0] = __floats2half2_rn(w1024.r, w1024.i); t[1] = hcm(t[0], m128);
    t[2] = hcm(t[0], m256); t[3] = hcm(t[1], m256);
#pragma unroll
    for (int i = 0; i < 4; i++) t[4 + i] = hcm(t[i], m512);
    put(t); get(T4, ad.lb);
  }
  k2048 = (C.r * we.r + C.i * we.i) * sc;
#pragma unroll
  for (int i = 0; i < 8; i++) {
    const uint32_t z = A0[i >> 2][i & 3];
    A[i >> 1][2 * (i & 1)] = z;
    A[i >> 1][2 * (i & 1) + 1] = fmul(z, rot(z), M[0][i >> 2][i & 3]);
  }
  tile(0, T0);
#pragma unroll
  for (int i = 0; i < 8; i++) {
    const uint32_t z = T0[i >> 2][i & 3], zi = rot(z);
#pragma unroll
    for (int j = 1; j < 4; j++) M[j][i >> 2][i & 3] = fmul(z, zi, M[j][i >> 2][i & 3]);
  }
  tile(4, T4); tile(1, M[1]); tile(2, M[2]); tile(3, M[3]);
}

__device__ __forceinline__ void build_tables(uint32_t tb, int lane, float (&k)[5][4], float k2048) {
  const int g = lane >> 2, c = lane & 3;
  const uint32_t kc = tb + T_KC + 16;
  {
    const uint32_t a0 = kc + 16 * g + 4 * c, a2 = kc + 2 * (256 + 4 * g + c);
    const uint32_t a3 = kc + 2 * (384 + 2 * g + 64 * (c & 1) + (c >> 1)), a4 = kc + 2 * (512 + g + 32 * c);
#pragma unroll
    for (int r = 0; r < 2; r++) {
      sts32(a0 + 128 * r, pack_bf(k[0][2 * r], k[0][2 * r + 1]));
      sts32(a0 + 128 * r + 256, pack_bf(k[1][2 * r], k[1][2 * r + 1]));
      const uint32_t w2 = pack_bf(k[2][2 * r], k[2][2 * r + 1]);
      const uint32_t w3 = pack_bf(k[3][2 * r], k[3][2 * r + 1]);
      const uint32_t w4 = pack_bf(k[4][2 * r], k[4][2 * r + 1]);
      sts16(a2 + 64 * r, w2); sts16(a2 + 64 * r + 128, w2 >> 16);
      sts16(a3 + 32 * r, w3); sts16(a3 + 32 * r + 64, w3 >> 16);
      sts16(a4 + 16 * r, w4); sts16(a4 + 16 * r + 32, w4 >> 16);
    }
  }
  if (lane == 0) { sts16(kc + 2 * 640, pack_bf(k2048, 0.f)); sts32(kc - 4, 0); }
  __syncwarp();
  const uint32_t td = tb + T_D + 32;
#pragma unroll
  for (int hf = 0; hf < 2; hf++) {
    const uint2 v = lds64(kc + 256 * hf + 8 * lane);
    const uint32_t pv = lds32(kc + 256 * hf + 8 * lane - 4);
    sts128(td + 512 * hf + 16 * lane, __byte_perm(v.x, pv, 0x7610), __byte_perm(v.x, v.x, 0x1032), __byte_perm(v.y, v.x, 0x7610),
           __byte_perm(v.y, v.y, 0x1032));
  }
#pragma unroll
  for (int hf = 0; hf < 2; hf++) {
    const uint32_t v = lds32(kc + 512 + 128 * hf + 4 * lane), nx = lds32(kc + 516 + 128 * hf + 4 * lane);
    uint32_t w0 = __byte_perm(v, v, 0x1010);
    const uint32_t w1 = w0;
    if (hf == 0) { const uint32_t pv = lds32(kc + 508); if (lane == 0) w0 = __byte_perm(v, pv, 0x7610); }
    sts128(td + 1024 + 512 * hf + 16 * lane, w0, w1, __byte_perm(v, v, 0x1032), __byte_perm(nx, v, 0x7610));
  }
  {
    const uint32_t kk = lds16(kc + 2 * 384);
    const uint32_t w = lane < 3 ? (kk | (kk << 16)) : (lane == 3 ? (kk << 16) : 0u);
    if (lane < 24) sts32(td + 4 * (lane < 16 ? 512 + lane : lane - 24), w);
    const uint32_t lo_ = lds16(kc + 2 * 511), le_ = lds16(kc + 2 * 512);
    const uint32_t ja = tb + T_5 + (lane < 16 ? 4 * lane : 256 + 4 * lane);
    sts32(ja, lane == 16 ? (le_ << 16) : 0u);
    sts32(ja + 384, lane == 16 ? (lo_ << 16) : 0u);
    sts32(tb + (lane < 16 ? T_7 : T_9 - 64) + 4 * lane, 0u);
  }
#pragma unroll
  for (int s = 0; s < 2; s++) {
    const uint32_t b = kc + 2 * (s ? 512 : 384) + 8 * lane;
    const uint2 v = lds64(b);
    uint32_t em = lds16(b - 2), e0 = v.x;
    const uint32_t e4 = lds16(b + 8);
    if (lane == 0) { em = 0; e0 = 0; }
    sts64(tb + (s ? T_7 : T_3) + 64 + 8 * lane, __byte_perm(v.x, em, 0x5432), __byte_perm(v.y, v.x, 0x7632));
    sts64(tb + (s ? T_9 : T_5) + 64 + 8 * lane, __byte_perm(v.y, e0, 0x5410), __byte_perm(e4, v.y, 0x5410));
  }
  __syncwarp();
}

__device__ __forceinline__ uint32_t box2w(int lo, int n, int o) {
  return ((unsigned)(o - lo) < (unsigned)n ? 0x3F80u : 0u) | ((unsigned)(o + 1 - lo) < (unsigned)n ? 0x3F800000u : 0u);
}

__device__ __forceinline__ void conv_channel(uint32_t ub, uint32_t tb, int lane, uint4* ydst) {
  const int g = lane >> 2, c = lane & 3, x = g - 2 * c;
  const int mi = lane >> 3;
  const uint32_t qa = ub + U_PAD + 16 * (lane & 7) + ((mi == 0 || mi == 3) ? U_ODD : 0) - (mi == 0 ? 16 : 0);
  const uint32_t hb = ub + U_PAD + (mi & 1) * U_ODD + 16 * ((lane >> 4) + (lane & 7)) - 16;
  const uint32_t kv = lds16(tb + T_KC + 16 + 2 * 512);
  const int oh = c < 2 ? 8 + 2 * c : 2 * c - 8, og = c < 3 ? 2 * c : -10;
  uint32_t bx[4] = {box2w(g - 4, 9, 2 * c), box2w(g - 3, 7, 2 * c), box2w(g - 4, 9, oh), box2w(g - 3, 7, oh)};
  uint32_t by[4] = {box2w(g - 10, 5, 2 * c - 8), box2w(g - 5, 3, 2 * c - 8), box2w(g - 10, 5, og), box2w(g - 5, 3, og)};
  uint32_t lb0 = ((unsigned)(x + 5) < 2u ? kv : 0u) | ((unsigned)(x + 4) < 2u ? kv << 16 : 0u);
  uint32_t lb1 = ((unsigned)(x - 3) < 2u ? kv : 0u) | ((unsigned)(x - 4) < 2u ? kv << 16 : 0u);
  const int q0 = g - 1, q1 = c < 3 ? g : g - 2;
  uint32_t y0a = ub + U_PAD + (q0 & 1) * U_ODD + 16 * (q0 >> 1) + 4 * c;
  uint32_t y1a = ub + U_PAD + (q1 & 1) * U_ODD + 16 * (q1 >> 1) + 4 * c;
#pragma unroll
  for (int i = 0; i < 4; i++) asm volatile("" : "+r"(bx[i]), "+r"(by[i]));
  asm volatile("" : "+r"(lb0), "+r"(lb1), "+r"(y0a), "+r"(y1a));
  mbar_wait(BAR(MB_UFULL));
  mbar_spin(BAR(MB_EMPTY + 15));
  TS(36);
  float acc[16][4];
  {
    uint32_t z09[8], z07[8], zm9[8], zm7[8];
#pragma unroll
    for (int i = 0; i < 8; i++) {
      uint32_t h[4];
      ldsm4(h, hb + 128 * i);
      float y0, y1, y2, y3, w0, w1, w2, w3;
      mma0(y0, y1, y2, y3, bx[0], bx[1], bx[2], bx[3], h[2], c < 2 ? h[3] : h[1]);
      mma0(w0, w1, w2, w3, bx[0], bx[1], bx[2], bx[3], h[1], c < 2 ? h[2] : h[0]);
      z09[i] = pack_bf(y0, y1); z07[i] = pack_bf(y2, y3);
      zm9[i] = pack_bf(w0, w1); zm7[i] = pack_bf(w2, w3);
    }
  uint32_t f3[3][4][4];
  {
    const uint32_t fa = tb + T_7 + 4 * (16 + x);
#pragma unroll
    for (int tt = 0; tt < 3; tt++)
#pragma unroll
      for (int D = 0; D < 4; D++) {
        const uint32_t a = fa + (tt == 0 ? 316 : (tt == 1 ? 320 : 0)) + 64 * D;
        f3[tt][D][0] = lds32(a); f3[tt][D][1] = lds32(a + 32); f3[tt][D][2] = lds32(a - 32); f3[tt][D][3] = lds32(a);
      }
  }
    float a[4][2][4];
#pragma unroll
    for (int kap = 0; kap < 4; kap++)
#pragma unroll
      for (int sg = 0; sg < 2; sg++)
#pragma unroll
        for (int bk = 3; bk >= kap; bk--) {
          const uint32_t(&q0_)[4] = f3[sg ? 2 : 0][bk - kap];
          const uint32_t(&q1_)[4] = f3[sg ? 2 : 1][bk - kap];
          float(&a0)[4] = a[bk][0];
          float(&a1)[4] = a[bk][1];
          if (sg == 0 && kap == 0) {
            mma0(a0[0], a0[1], a0[2], a0[3], q0_[0], q0_[1], q0_[2], q0_[3], z09[0], z09[1]);
            mma0(a1[0], a1[1], a1[2], a1[3], q1_[0], q1_[1], q1_[2], q1_[3], zm9[0], zm9[1]);
          } else {
            mma(a0[0], a0[1], a0[2], a0[3], q0_[0], q0_[1], q0_[2], q0_[3], sg ? zm7[2 * kap] : z09[2 * kap], sg ? zm7[2 * kap + 1] : z09[2 * kap + 1]);
            mma(a1[0], a1[1], a1[2], a1[3], q1_[0], q1_[1], q1_[2], q1_[3], sg ? z07[2 * kap] : zm9[2 * kap], sg ? z07[2 * kap + 1] : zm9[2 * kap + 1]);
          }
        }
    SPLIT();
#pragma unroll
    for (int i = 0; i < 8; i++) {
      uint32_t h[4];
      ldsm4(h, qa + 128 * i);
      const float ci[4] = {a[i >> 1][0][2 * (i & 1)], a[i >> 1][0][2 * (i & 1) + 1], a[i >> 1][1][2 * (i & 1)], a[i >> 1][1][2 * (i & 1) + 1]};
      mmac(acc[8 + i], h[0], h[1], h[2], h[3], lb0, lb1, ci);
    }
  }
  TS(44);
  {
    uint2 a5[10], a3[10];
    const uint32_t aa = tb + T_5 + 4 * (8 + 2 * g - 2 * c);
#pragma unroll
    for (int m = 0; m < 10; m++) { a5[m] = lds64(aa + 32 * m); a3[m] = lds64(aa + 384 + 32 * m); }
    uint32_t x5[12][2], x3[12][2];
    auto ygen = [&](int kap) {
#pragma unroll
      for (int hh = 0; hh < 2; hh++) {
        float y0, y1, y2, y3;
        mma0(y0, y1, y2, y3, by[0], by[1], by[2], by[3], lds32(y0a + 128 * kap + 64 * hh), lds32(y1a + 128 * kap + 64 * hh));
        x5[kap][hh] = pack_bf(y0, y1);
        x3[kap][hh] = pack_bf(y2, y3);
      }
    };
    ygen(11); ygen(10); ygen(9); ygen(8);
#pragma unroll
    for (int kap = 11; kap >= 0; kap--) {
      if (kap >= 4) ygen(kap - 4);
#pragma unroll
      for (int sg = 0; sg < 2; sg++)
#pragma unroll
        for (int i = 4; i >= 0; i--) {
          const int be = kap + 4 + i;
          if (be <= 15) {
            const uint2 &hi = sg ? a3[2 * i + 1] : a5[2 * i + 1], &lo = sg ? a3[2 * i] : a5[2 * i];
            const uint32_t b0 = sg ? x3[kap][0] : x5[kap][0], b1 = sg ? x3[kap][1] : x5[kap][1];
            if (be < 8 && i == 0 && sg == 0) mma0(acc[be][0], acc[be][1], acc[be][2], acc[be][3], hi.x, hi.y, lo.x, lo.y, b0, b1);
            else mma(acc[be][0], acc[be][1], acc[be][2], acc[be][3], hi.x, hi.y, lo.x, lo.y, b0, b1);
          }
        }
    }
  }
  TS(45);
  {
    const uint32_t st = tb + T_ST + lane * 8;
#pragma unroll
    for (int be = 4; be < 12; be++) sts64(st + 256 * be, pack_bf(acc[be][0], acc[be][1]), pack_bf(acc[be][2], acc[be][3]));
    SPLIT();
    uint32_t F[66], qd[8][4];
    const uint32_t fa = tb + T_D + 32 + 4 * x;
#pragma unroll
    for (int i = 0; i < 32; i++) {
      const int s = 120 - (i >> 2) - 8 * (i & 3);
      uint32_t(&q)[4] = qd[i & 7];
      ldsm4(q, qa + 16 * s);
      const int m = 16 * (i & 3) + 2 * (i >> 2);
      F[m] = lds32(fa + 32 * m); F[m + 1] = lds32(fa + 32 * m + 32);
#pragma unroll
      for (int be = 15; be >= 12; be--) {
        const int de = 8 * be - s;
        float(&a)[4] = (be >= 14 && !(i & 1)) ? acc[be - 4] : acc[be];
        if (de >= 0 && be >= 14 && i == 2 * (15 - be)) mma0(a[0], a[1], a[2], a[3], q[0], q[1], q[2], q[3], F[2 * de + 1], F[2 * de]);
        else if (de >= 0) mma(a[0], a[1], a[2], a[3], q[0], q[1], q[2], q[3], F[2 * de + 1], F[2 * de]);
      }
    }
#pragma unroll
    for (int i = 0; i < 8; i++) acc[14 + (i >> 2)][i & 3] += acc[10 + (i >> 2)][i & 3];
    F[64] = lds32(fa + 32 * 64); F[65] = lds32(fa + 32 * 65);
    uint32_t qp = qa + 128 * 11, sta = st + 256 * 10;
    uint4* yd = ydst + 7 * 32;
#pragma unroll
    for (int i = 0; i < 6; i++) ldsm4(qd[i], qp - 16 * i);
    uint2 sv = lds64(sta + 256);
    float ci[4] = {bf_lo(sv.x), bf_hi(sv.x), bf_lo(sv.y), bf_hi(sv.y)};
    float T[5][4];
#pragma unroll
    for (int i = 0; i < 16; i++) T[i >> 2][i & 3] = acc[12 + (i >> 2)][i & 3];
    nb_sync(NB_YZ, 160);
    TS(46);
#pragma unroll 1
    for (int bp = 5; bp >= 0; bp--) {
      uint32_t held[2];
#pragma unroll
      for (int o = 1; o >= 0; o--) {
#pragma unroll
        for (int k = 4; k >= 1; k--) mmac(T[k], qd[0][0], qd[0][1], qd[0][2], qd[0][3], F[16 * k + 1], F[16 * k], T[k - 1]);
        mmac(T[0], qd[0][0], qd[0][1], qd[0][2], qd[0][3], F[1], F[0], ci);
        ldsm4(qd[6], qp - 16 * 6);
        ldsm4(qd[7], qp - 16 * 7);
        sv = lds64(sta);
#pragma unroll
        for (int i = 1; i < 8; i++) {
#pragma unroll
          for (int k = 3; k >= 0; k--)
            mma(T[k][0], T[k][1], T[k][2], T[k][3], qd[i][0], qd[i][1], qd[i][2], qd[i][3], F[16 * k + 2 * i + 1], F[16 * k + 2 * i]);
          if (i < 7) ldsm4(qd[i - 1], qp - 128 - 16 * (i - 1));
          if (i == 2) {
            const uint32_t w0 = pack_bf(T[4][0], T[4][1]), w1 = pack_bf(T[4][2], T[4][3]);
            if (o) { held[0] = w0; held[1] = w1; }
            else st_x(yd, nz(w0), w1, held[0], held[1]);
          }
          if (i == 4) {
            if (2 * bp + o <= 4) sv = make_uint2(0, 0);
            ci[0] = bf_lo(sv.x); ci[1] = bf_hi(sv.x); ci[2] = bf_lo(sv.y); ci[3] = bf_hi(sv.y);
          }
        }
        qp -= 128; sta -= 256;
      }
      yd -= 32;
      if (!(bp & 1)) nb_arrive(NB_Y + 1 + (bp >> 1), 160);
    }
#pragma unroll
    for (int B = 1; B >= 0; B--)
      st_x(ydst + B * 32, nz(pack_bf(T[2 * B][0], T[2 * B][1])), pack_bf(T[2 * B][2], T[2 * B][3]),
           pack_bf(T[2 * B + 1][0], T[2 * B + 1][1]), pack_bf(T[2 * B + 1][2], T[2 * B + 1][3]));
  }
}

__device__ __forceinline__ void dual_exp(const uint32_t* w, uint32_t* e) {
  const float L = 1.44268798828125f;
  uint32_t mx = bmax2(bmax2(w[0], w[1]), bmax2(w[2], w[3]));
  uint32_t mn = bmin2(bmin2(w[0], w[1]), bmin2(w[2], w[3]));
  mx = bmax2(mx, __shfl_xor_sync(0xffffffffu, mx, 1));
  mn = bmin2(mn, __shfl_xor_sync(0xffffffffu, mn, 1));
  mx = bmax2(mx, __shfl_xor_sync(0xffffffffu, mx, 2));
  mn = bmin2(mn, __shfl_xor_sync(0xffffffffu, mn, 2));
  const float mx0 = bf_lo(mx) * -L, mx1 = bf_hi(mx) * -L, mn0 = bf_lo(mn) * L, mn1 = bf_hi(mn) * L;
#pragma unroll
  for (int i = 0; i < 2; i++) {
    const float a0 = bf_lo(w[2 * i]), a1 = bf_hi(w[2 * i]), b0 = bf_lo(w[2 * i + 1]), b1 = bf_hi(w[2 * i + 1]);
    e[2 * i] = pack_bf(ex2(fmaf(a0, L, mx0)), ex2(fmaf(b0, L, mx0)));
    e[2 * i + 1] = pack_bf(ex2(fmaf(a1, L, mx1)), ex2(fmaf(b1, L, mx1)));
    e[4 + 2 * i] = pack_bf(ex2(fmaf(a0, -L, mn0)), ex2(fmaf(b0, -L, mn0)));
    e[5 + 2 * i] = pack_bf(ex2(fmaf(a1, -L, mn1)), ex2(fmaf(b1, -L, mn1)));
  }
}
__device__ __forceinline__ void normalise(uint32_t* e, const float (&s)[4]) {
  const uint32_t r = pack_bf(rcp(s[0]), rcp(s[2]));
  const __nv_bfloat162 rr = *(const __nv_bfloat162*)&r;
#pragma unroll
  for (int i = 0; i < 4; i++) {
    const __nv_bfloat162 v = __hmul2(*(const __nv_bfloat162*)&e[i], (i & 1) ? __high2bfloat162(rr) : __low2bfloat162(rr));
    e[i] = *(const uint32_t*)&v;
  }
}
__host__ __device__ constexpr uint64_t qdesc(uint32_t addr) { return mkdesc(addr, 128, 256, 0); }

__global__ void __launch_bounds__(NTHREADS, 1)
fused_kernel(const Params P, const __grid_constant__ CUtensorMap mx, const __grid_constant__ CUtensorMap mw,
             const __grid_constant__ CUtensorMap mo, const __grid_constant__ CUtensorMap mu,
             const __grid_constant__ CUtensorMap mout, const __grid_constant__ CUtensorMap mw4) {
  constexpr uint32_t sb = SB;
  const int tid = threadIdx.x, lane = tid & 31;
  const int warp = __shfl_sync(0xffffffffu, tid >> 5, 0);
  const int b = blockIdx.x, oct = b >> 3, i8 = b & 7;
  const int rt = (((oct & 4) ? ~oct : oct) & 3) * 2 + (i8 >> 2);
  const int hp = (oct >> 2) * 4 + (i8 & 3);

  const int wg = warp >> 2, w = warp & 3;
  const int d = b * 4 + ((tid >> 5) & 3);
  const KgenRaw raw = kgen_load(P, d, tid >> 7, lane);
  const unsigned short dsk = __ldg((const unsigned short*)P.Dskip + d);
  if (warp == 15) {
    asm volatile("prefetch.tensormap [%0];" ::"l"(&mu) : "memory");
    asm volatile("prefetch.tensormap [%0];" ::"l"(&mw) : "memory");
    asm volatile("prefetch.tensormap [%0];" ::"l"(&mx) : "memory");
    asm volatile("prefetch.tensormap [%0];" ::"l"(&mw4) : "memory");
  }
  if (warp == 12) {
    if (lane == 0) {
#pragma unroll
      for (int i = 0; i < 9; i++) mbar_init(BAR(i), 1);
      asm volatile("fence.mbarrier_init.release.cluster;" ::: "memory");
    }
    __syncwarp();
    if (lane < 9) mbar_expect(BAR(0) + 8 * lane, (lane == 5 || lane == 7) ? 40960 : ((lane == 0 || lane > 5) ? 16384 : 28672));
    __syncwarp();
    e_tma3d(sb + OFF_W, &mw, BAR(MB_FULL), hp * 32, 0, 0);
    e_tma2d(sb + OFF_X + 3 * 16384, &mx, BAR(MB_FULL), 0, rt * 256);
    nb_arrive(NB_PROD, 512);
  } else if (warp == 14) {
    e_prefetch(P.x + (size_t)(rt * 256 + hp * 8) * 512, 8192);
  } else if (warp == 13) {
    if (lane == 0) {
#pragma unroll
      for (int i = 9; i < 40; i++) mbar_init(BAR(i), i < MB_EMPTY ? 1 : 4);
      asm volatile("fence.mbarrier_init.release.cluster;" ::: "memory");
    }
    __syncwarp();
    if (lane < 14 && lane != 9) mbar_expect(BAR(MB_FULL + 8) + 8 * lane, lane == 8 ? 131072 : (lane == 10 ? 8192 : (lane == 13 ? 24576 : 16384)));
    nb_arrive(NB_PROD, 512);
  }
  const uint32_t tb = sb + OFF_T + w * T_CH;
  const uint32_t kp = wg == 2 ? sb + OFF_STG0 + 16384 + w * 1024 : ((tb + 127) & ~127u) + (wg == 3 ? 2 : wg) * 1536;
  const KgenAddr kad = kgen_addr(lane, kp);
  if ((warp >> 1) != 6) nb_sync(NB_PROD, 512);
  else nb_sync(NB_GATE + 1, 64);
  if (warp == 12) {
#pragma unroll 1
    for (int kb = 1; kb < 4; kb++) {
      if (kb == U_AT) e_tma4d(sb + OFF_STG0, &mu, BAR(MB_URAW), i8 * 64, oct * 2);
      e_tma3d(sb + OFF_W + kb * 12288, &mw, BAR(MB_FULL) + 8 * kb, hp * 32, kb * 64, 0);
      e_tma2d(sb + OFF_X + (kb < 2 ? kb + 3 : kb - 2) * 16384, &mx, BAR(MB_FULL) + 8 * kb, kb * 64, rt * 256);
    }
    e_tma4d(sb + OFF_W + 4 * 12288, &mw4, BAR(MB_FULL + 4), hp * 32, 4);
    e_tma2d(sb + OFF_X + 2 * 16384, &mx, BAR(MB_FULL + 4), 256, rt * 256);
    e_tma4d(sb + OFF_W + 6 * 12288, &mw4, BAR(MB_FULL + 6), hp * 32, 6);
    if (smem_u32(smem_raw) != SB) __trap();
    if (lane == 0) TS1(54);
  }
  float k[5][4], k2048, ksc;
  kgen_unit(raw, kad, blockIdx.y, k, k2048, ksc);
  TS(40 + wg);
  if ((fu(k[0][0]) & fu(k[1][0]) & fu(k[2][0]) & fu(k[3][0]) & fu(k[4][0])) == 0xffffffffu) sts32(kp, 0);
  if (wg) nb_arrive(0, 512);
  k2048 += __shfl_xor_sync(0xffffffffu, k2048, 16);
  k2048 += __shfl_xor_sync(0xffffffffu, k2048, 8);
  if (wg != 2) {
    uint32_t h[10];
#pragma unroll
    for (int j = 0; j < 10; j++) h[j] = hu(__floats2half2_rn(k[j >> 1][2 * (j & 1)], k[j >> 1][2 * (j & 1) + 1]));
    sts128(kp + lane * 16, h[0], h[1], h[2], h[3]);
    sts128(kp + 512 + lane * 16, h[4], h[5], h[6], h[7]);
    sts128(kp + 1024 + lane * 16, h[8], h[9], fu(k2048), fu(ksc));
  }
  if (wg == 0) { nb_arrive(NB_PREP, 512); nb_sync(0, 512); }
  else if (wg != 2) nb_arrive(NB_PREP, 512);
  else nb_sync(NB_PREP, 512);
  if (warp >= 12) {
    asm volatile("setmaxnreg.dec.sync.aligned.u32 32;");
    if (warp == 12) {
      if (X2_AT < 0) e_prefetch(P.x + (size_t)(rt * 256 + 128 + hp * 8) * 512, 8192);
      uint32_t slot = sb + OFF_X + 3 * 16384;
#pragma unroll 1
      for (int n = 0; n < 11; n++) {
        mbar_spin(BAR(MB_EMPTY) + 8 * n);
        const int m = n + 5;
        e_tma2d(slot, &mx, BAR(MB_FULL) + 8 * m, (m & 7) * 64, rt * 256 + (m >> 3) * 128);
        slot = slot == sb + OFF_X + 4 * 16384 ? sb + OFF_X : slot + 16384;
        if (n == X2_AT) e_prefetch(P.x + (size_t)(rt * 256 + 128 + hp * 8) * 512, 8192);
        if (n == 7) {
          e_prefetch(P.wo + (size_t)b * 2048, 4096);
          asm volatile("prefetch.tensormap [%0];" ::"l"(&mo) : "memory");
          asm volatile("prefetch.tensormap [%0];" ::"l"(&mout) : "memory");
        }
      }
#pragma unroll 1
      for (int i = 0; i < 8; i++) {
        mbar_wait(BAR(MB_EMPTY + 10) + 8 * ((0x54332222u >> (4 * i)) & 7));
        const int w0 = (0x54736210u >> (4 * i)) & 7;
        e_tma3d(sb + OFF_W + w0 * 16384, &mo, BAR(MB_WO), 0, w0 * 64, (hp & 3) * 2);
      }
    } else {
      if (warp == 15) {
        const uint4 v0 = __ldg((const uint4*)P.wphi + hp * 64 + lane), v1 = __ldg((const uint4*)P.wphi + hp * 64 + 32 + lane);
        sts128(sb + OFF_PHI + (lane & 1) * 256 + (lane >> 1) * 16, v0.x, v0.y, v0.z, v0.w);
        sts128(sb + OFF_PHI + 512 + (lane & 1) * 256 + (lane >> 1) * 16, v1.x, v1.y, v1.z, v1.w);
        const uint32_t one = (((lane >> 3) ^ (lane >> 4)) & 1) ? 0u : ((lane & 1) ? 0x3F800000u : 0x3F80u);
        const int q = (lane >> 1) & 3;
        sts128(sb + OFF_EYE + lane * 16, q == 0 ? one : 0u, q == 1 ? one : 0u, q == 2 ? one : 0u, q == 3 ? one : 0u);
        sts64(sb + OFF_ONE + lane * 8, 0x3F803F80u, 0x3F803F80u);
        asm volatile("fence.proxy.async.shared::cta;" ::: "memory");
        nb_arrive(NB_KREAD, 160);
      }
      uint32_t* cnt = (uint32_t*)(P.xs + X_CNT) + (warp == 13 ? i8 : (warp == 14 ? 8 + rt : 16 + oct)) * 32;
      const unsigned target = (ld_x32(cnt) & ~15u) + 16;
      if (warp != 14) {
        if (warp == 15) mbar_wait(BAR(MB_EMPTY + ZERO_STEP));
        uint4* pz = P.xs + (warp == 13 ? X_PART + (hp * 8 + rt) * 144 : X_Y + b * 1024) + lane;
#pragma unroll 1
        for (int i = (warp == 13 ? 144 : 1024) - lane; i > 0; i -= 32, pz += 32) st_x(pz, 0, 0, 0, 0);
      }
      if (warp == 15) __syncwarp();
      else nb_sync(warp == 13 ? NB_INIT : NB_ODONE, warp == 13 ? 160 : 288);
      if (lane == 0) asm volatile("red.release.gpu.global.add.u32 [%0], %1;" ::"l"(cnt), "r"(warp == 15 ? 2 : 1) : "memory");
      if (lane == 0) TS1(warp == 13 ? 50 : (warp == 14 ? 57 : 53));
      asm volatile("fence.proxy.async.shared::cta;" ::: "memory");
      if (warp == 13) cnt += ((lane & 1 ? b >> 4 : i8 ^ (lane & 4)) - i8) * 32;
#pragma unroll 1
      for (int i = 0; i < SPIN_MAX; i++) {
        unsigned v;
        asm volatile("ld.acquire.gpu.global.u32 %0, [%1];" : "=r"(v) : "l"(cnt) : "memory");
        if (__all_sync(0xffffffffu, (int)(v - target) >= 0)) break;
      }
      if (lane == 0) TS1(warp == 13 ? 51 : (warp == 14 ? 58 : 55));
      if (warp == 15) { nb_arrive(NB_YZ, 160); return; }
      asm volatile("fence.proxy.async.global;" ::: "memory");
      if (warp == 13) {
        mbar_wait(BAR(MB_EMPTY + 11));
        e_expect(BAR(MB_UFULL), 4 * U_CH);
        e_bulk(sb + OFF_U, P.xs + X_UT + b * (U_CH / 4), 4 * U_CH, BAR(MB_UFULL));
      } else {
        const uint4* src = P.xs + X_O + (rt * 4 + (hp >> 2)) * 4096;
        e_bulk(sb + OFF_X + 32768 + 57344, src + 3584, 8192, BAR(MB_O));
        e_bulk(sb + OFF_X + 32768, src, 16384, BAR(MB_O + 1));
        e_bulk(sb + OFF_X + 49152, src + 1024, 16384, BAR(MB_O + 2));
        e_bulk(sb + OFF_STG0, src + 3200, 6144, BAR(MB_O + 3));
        nb_sync(NB_BDONE, 288);
        asm volatile("fence.proxy.async.shared::cta;" ::: "memory");
        e_bulk(sb + OFF_U, src + 2048, 18432, BAR(MB_O + 3));
      }
    }
    return;
  }

  const int t = tid & 127;
  const int g = lane >> 2, c = lane & 3;
  if (wg == 1) {
    mbar_wait(BAR(MB_URAW));
    TS(48);
    uint4* dst = P.xs + X_UT + (i8 * 64 + g) * (U_CH / 16) + (w & 1) * (U_ODD / 16) + U_PAD / 16 + oct * 8 + (w >> 1) * 4 + c;
    const int ln = ((lane >> 1) & 3) + 4 * (lane & 1);
    uint32_t r[8][4];
#pragma unroll
    for (int i = 0; i < 8; i++) ldsm4t(r[i], sb + OFF_STG0 + w * 4096 + ((lane >> 3) * 8 + ln) * 128 + ((i ^ ln) << 4));
#pragma unroll
    for (int i = 0; i < 8; i++) dst[i * (U_CH / 2)] = make_uint4(r[i][0], r[i][1], r[i][2], r[i][3]);
    nb_arrive(NB_INIT, 160);
    if (lane == 0) mbar_arrive(BAR(MB_AUX));
  }
  {
    if (wg == 2) {
      asm volatile("setmaxnreg.inc.sync.aligned.u32 160;");
#pragma unroll
      for (int j = 0; j < 5; j++) { k[j][0] *= ksc; k[j][1] *= ksc; k[j][2] *= ksc; k[j][3] *= ksc; }
#pragma unroll 1
      for (int q = 0; q < 3; q++) {
        const uint32_t src = ((tb + 127) & ~127u) + q * 1536 + lane * 16;
        const uint4 v0 = lds128(src), v1 = lds128(src + 512), v2 = lds128(src + 1024);
        const uint32_t h[10] = {v0.x, v0.y, v0.z, v0.w, v1.x, v1.y, v1.z, v1.w, v2.x, v2.y};
#pragma unroll
        for (int j = 0; j < 10; j++) {
          const float2 f = __half22float2(*(const __half2*)&h[j]);
          k[j >> 1][2 * (j & 1)] = fmaf(f.x, uf(v2.w), k[j >> 1][2 * (j & 1)]);
          k[j >> 1][2 * (j & 1) + 1] = fmaf(f.y, uf(v2.w), k[j >> 1][2 * (j & 1) + 1]);
        }
        k2048 += uf(v2.z);
      }
#pragma unroll
      for (int o2 = 4; o2; o2 >>= 1) k2048 += __shfl_xor_sync(0xffffffffu, k2048, o2);
      if (lane == 0) k[0][0] += bf_lo(dsk);
      __syncwarp();
      TS(34);
      build_tables(tb, lane, k, k2048);
      TS(35);
      uint4* const g_y = P.xs + X_Y;
      conv_channel(sb + OFF_U + w * U_CH, tb, lane, g_y + (size_t)d * 256 + lane);
      nb_arrive(NB_BDONE, 288);
      nb_arrive(NB_Y, 160);
      TS(37);
      if (w == 0) TSDUMP(32);
      return;
    }
    if (wg == 1) {
      mbar_wait(BAR(MB_EMPTY + 4));
      mbar_spin(BAR(MB_EMPTY + 6));
    }
    TS(wg * 16 + 1);
  }

  float acc[2][48];
  {
    uint32_t fb = BAR(MB_FULL) + 64 * wg;
    uint32_t da = (uint32_t)mkdesc(sb + OFF_X, 16, 0, 0) + (wg ? 1024 : 3072), db = (uint32_t)mkdesc(sb + OFF_W, 4096, 0, 0);
    constexpr uint64_t ha = mkdesc(0, 0, 1024, 1), hb = mkdesc(0, 0, 512, 2);
    mbar_spin(fb);
    TS(wg * 16 + 2);
#pragma unroll 1
    for (int kb = 0; kb < 8; kb++) {
      WG_FENCE();
#pragma unroll
      for (int k = 0; k < 4; k++) {
        wgmma_ss_n96(acc[0], ha | (da + 2 * k), hb | (db + 64 * k), k ? 1 : kb);
        wgmma_ss_n96(acc[1], ha | (da + 2 * k + 512), hb | (db + 64 * k), k ? 1 : kb);
      }
      WG_COMMIT();
      if (kb < 7) mbar_spin(fb + 8);
      WG_WAIT(1);
      if (kb > 0) e_arrive(fb + 8 * (MB_EMPTY - MB_FULL - 1));
      fb += 8; db += 768;
      da = da == (uint32_t)mkdesc(sb + OFF_X + 65536, 16, 0, 0) ? da - 4096 : da + 1024;
    }
    if (wg == 0) nb_sync(NB_KREAD, 160);
    asm volatile("setmaxnreg.inc.sync.aligned.u32 160;");
    WG_WAIT(0);
    e_arrive(fb + 8 * (MB_EMPTY - MB_FULL - 1));
    SPLIT();
  }
  TS(wg * 16 + 3);

  constexpr uint32_t stg0 = sb + OFF_STG0, stg1 = sb + OFF_X + 32768;
  uint4* const g_part = P.xs + X_PART;
  uint4* const g_o = P.xs + X_O;
  constexpr uint32_t kvs = stg0;
  auto pack8 = [](const float* a) { return make_uint4(pack_bf(a[0], a[1]), pack_bf(a[2], a[3]), pack_bf(a[4], a[5]), pack_bf(a[6], a[7])); };
  auto feat = [&](const uint4 (&af)[4], float (&p)[4][8]) {
    WG_FENCE();
#pragma unroll
    for (int u = 0; u < 4; u++) wgmma_rs_n16(p[u], af[u], qdesc(sb + OFF_PHI + (u & 1) * 512), 0);
    WG_COMMIT();
  };
  auto packp = [](const float (&p)[4][8], uint32_t (&pw)[16]) {
#pragma unroll
    for (int i = 0; i < 16; i++) pw[i] = pack_bf(p[i >> 2][(i & 1) + 2 * (i & 2)], p[i >> 2][(i & 1) + 2 * (i & 2) + 2]);
  };
  auto contract = [&](float (&kc)[20], uint32_t stg, int acc_in) {
    WG_FENCE();
#pragma unroll
    for (int s = 0; s < 8; s++) wgmma_ss_n40(kc, qdesc(stg + s * SLAB), qdesc(stg + s * SLAB + 2048), s ? 1 : acc_in);
    WG_COMMIT();
    WG_WAIT(0);
  };
  uint32_t eq[32];
  {
    uint4 af[4], aq[4], vp[4];
    float p[4][8];
#pragma unroll
    for (int u = 0; u < 4; u++) af[u] = pack8(acc[u >> 1] + 16 + 8 * (u & 1));
    feat(af, p);
#pragma unroll
    for (int u = 0; u < 4; u++) { aq[u] = pack8(acc[u >> 1] + 8 * (u & 1)); vp[u] = pack8(acc[u >> 1] + 32 + 8 * (u & 1)); }
    WG_WAIT(0);
    uint32_t pw[16], ek[32];
    packp(p, pw);
#pragma unroll
    for (int u = 0; u < 4; u++) dual_exp(pw + 4 * u, ek + 8 * u);
    TS(wg * 16 + 12);
    mbar_spin(wg ? BAR(MB_EMPTY + 15) : BAR(MB_AUX));
    float rs[8][4];
    WG_FENCE();
#pragma unroll
    for (int i = 0; i < 8; i++) wgmma_rs_n8(rs[i], make_uint4(ek[4 * i], ek[4 * i + 1], ek[4 * i + 2], ek[4 * i + 3]), qdesc(sb + OFF_ONE), 0);
    WG_COMMIT();
    feat(aq, p);
    const uint32_t sl = (wg ? stg1 : stg0) + w * SLAB + lane * 16;
#pragma unroll
    for (int i = 0; i < 4; i++) stsm4(sl + (i >> 1) * 4 * SLAB + 2048 + (i & 1) * 512, vp[i].x, vp[i].y, vp[i].z, vp[i].w);
    sts128(sl + (lane >> 4) * (4 * SLAB - 256) + 3072, 0x3F803F80u, 0x3F803F80u, 0x3F803F80u, 0x3F803F80u);
    WG_WAIT(1);
#pragma unroll
    for (int i = 0; i < 8; i++) {
      normalise(ek + 4 * i, rs[i]);
      stsm4(sl + (i >> 2) * 4 * SLAB + (i & 3) * 512, ek[4 * i], ek[4 * i + 1], ek[4 * i + 2], ek[4 * i + 3]);
    }
    asm volatile("fence.proxy.async.shared::cta;" ::: "memory");
    TS(wg * 16 + 13);
    if (wg) {
      nb_arrive(NB_ST0, 256);
    } else {
      float kc[20];
      uint4* pp = g_part + (size_t)(hp * 8 + rt) * 144 + t;
      uint32_t* pz = (uint32_t*)(pp - t + 128) + w * 16 + c * 8 + g;
      asm volatile("" : "+l"(pp), "+l"(pz));
      nb_sync(NB_WG0, 128);
      contract(kc, stg0, 0);
      mbar_wait(BAR(MB_UFULL));
      TS(15);
      nb_sync(NB_ST0, 256);
      contract(kc, stg1, 1);
      TS(6);
      float kv[8];
#pragma unroll
      for (int i = 0; i < 8; i++) kv[i] = w & 2 ? kc[8 + i] : kc[i];
      st_x(pp, nz(pack_bf(kv[0], kv[1])), pack_bf(kv[2], kv[3]), pack_bf(kv[4], kv[5]), pack_bf(kv[6], kv[7]));
      if (c < 2) st_x32(pz, nz(fu(c ? kc[18] : kc[16])));
      TS(5);
    }
    SPLIT();
    WG_WAIT(0);
    packp(p, pw);
#pragma unroll
    for (int u = 0; u < 4; u++) dual_exp(pw + 4 * u, eq + 8 * u);
    SPLIT();
  }
  TS(wg * 16 + 4);
  if (wg == 1) {
    mbar_wait(BAR(MB_UFULL));
    const uint4* ps = g_part + (size_t)hp * 8 * 144 + t;
    const uint32_t* zs = (const uint32_t*)(g_part + (size_t)(hp * 8 + (lane >> 4) * 4) * 144 + 128) + w * 16 + (lane & 15);
    uint4 v[8];
    uint32_t zv[4];
#pragma unroll 1
    for (int it = 0; it < SPIN_MAX; it++) {
#pragma unroll
      for (int i = 0; i < 8; i++) v[i] = ld_x(ps + i * 144);
#pragma unroll
      for (int i = 0; i < 4; i++) zv[i] = ld_x32(zs + i * 576);
      uint32_t m = min(min(zv[0], zv[1]), min(zv[2], zv[3]));
#pragma unroll
      for (int i = 0; i < 8; i++) m = min(m, v[i].x);
      if (__all_sync(0xffffffffu, m != 0)) break;
    }
    float s[8];
    WG_FENCE();
#pragma unroll
    for (int r = 0; r < 8; r++) wgmma_rs_n16(s, v[r], qdesc(sb + OFF_EYE), r);
    WG_COMMIT();
    float zsum = (uf(zv[0]) + uf(zv[1])) + (uf(zv[2]) + uf(zv[3]));
    zsum += __shfl_xor_sync(0xffffffffu, zsum, 16);
    const uint32_t z1 = pack_bf(zsum, 1.f);
    if (lane < 16) sts128(kvs + w * 768 + 512 + lane * 16, z1, z1, z1, z1);
    WG_WAIT(0);
    stsm4(kvs + w * 768 + lane * 16, pack_bf(s[0], s[1]), pack_bf(s[2], s[3]), pack_bf(s[4], s[5]), pack_bf(s[6], s[7]));
    asm volatile("fence.proxy.async.shared::cta;" ::: "memory");
    TS(22);
  }
  nb_sync(NB_KV, 256);
  {
    float n[8][12];
    WG_FENCE();
#pragma unroll
    for (int i = 0; i < 8; i++) wgmma_rs_n24(n[i], make_uint4(eq[4 * i], eq[4 * i + 1], eq[4 * i + 2], eq[4 * i + 3]), qdesc(kvs + (i & 3) * 768), 0);
    WG_COMMIT();
    uint32_t* od = (uint32_t*)(g_o + (size_t)((rt * 4 + wg * 2) * 32 + hp * 2) * 128) + w * 64 + lane;
    WG_WAIT(0);
#pragma unroll
    for (int u = 0; u < 4; u++) {
      float(&np)[12] = n[2 * u];
      const float(&nm)[12] = n[2 * u + 1];
      const float q0 = np[9] * rcp(nm[9]), q1 = np[11] * rcp(nm[11]);
      const float r0 = rcp(fmaf(nm[8], q0, fmaf(np[9], 1e-6f, np[8]))), r1 = rcp(fmaf(nm[10], q1, fmaf(np[11], 1e-6f, np[10])));
#pragma unroll
      for (int i = 0; i < 8; i++) np[i] = fmaf(nm[i], (i & 2) ? q1 : q0, np[i]);
      uint32_t* o = od + (u >> 1) * 16384 + (u & 1) * 512;
      o[0] = pack_bf(np[0] * r0, np[1] * r0);
      o[32] = pack_bf(np[2] * r1, np[3] * r1);
      o[256] = pack_bf(np[4] * r0, np[5] * r0);
      o[288] = pack_bf(np[6] * r1, np[7] * r1);
      if (u == 1) SPLIT();
    }
  }
  TS(wg * 16 + 7);
  nb_arrive(NB_ODONE, 288);
  if (wg) {
    const uint4* src = P.xs + X_Y + (oct * 32 + c * 8) * 256 + (2 * w + (g >> 2)) * 32 + i8 * 4 + (g & 3);
    __nv_bfloat16* dst = P.out + (size_t)((2 * w + (g >> 2)) * 256 + i8 * 16 + (g & 3) * 2) * 1024 + 512 + oct * 32 + c * 8;
    nb_sync(NB_Y + w, 160);
    uint4 v[8];
#pragma unroll 1
    for (int it = 0; it < SPIN_MAX; it++) {
      uint32_t m = 0xffffffffu;
#pragma unroll
      for (int i = 0; i < 8; i++) v[i] = ld_x(src + i * 256);
#pragma unroll
      for (int i = 0; i < 8; i++) m = min(m, v[i].x);
      if (__all_sync(0xffffffffu, m != 0)) break;
    }
#pragma unroll
    for (int i = 0; i < 8; i++) *(uint4*)(dst + (size_t)((i >> 2) * 128 + ((i >> 1) & 1) * 8 + (i & 1)) * 1024) = tr_row(v, i);
    TS(31);
    GT(63);
    if (w == 0) TSDUMP(16);
    return;
  }
  mbar_wait(BAR(MB_WO));
  nb_sync(NB_BDONE, 288);
  TS(8);
  mbar_spin(BAR(MB_O));
  TS(9);
  constexpr uint64_t ha = mkdesc(0, 0, 128, 0), hb = mkdesc(0, 0, 1024, 1);
  constexpr uint32_t da0 = (uint32_t)mkdesc(stg1, 1024, 0, 0), db0 = (uint32_t)mkdesc(sb + OFF_W, 8192, 0, 0);
  const uint32_t ot = ((sb + OFF_T + 1023) & ~1023u) + w * 4096;
  auto store_half = [&](const float* oc, int hf) {
#pragma unroll
    for (int i = 0; i < 8; i += 2)
      stsm4(ot + hf * 2048 + (lane & 15) * 128 + (((i + (lane >> 4)) ^ lane) & 7) * 16, pack_bf(oc[4 * i], oc[4 * i + 1]),
            pack_bf(oc[4 * i + 2], oc[4 * i + 3]), pack_bf(oc[4 * i + 4], oc[4 * i + 5]), pack_bf(oc[4 * i + 6], oc[4 * i + 7]));
    asm volatile("fence.proxy.async.shared::cta;" ::: "memory");
    __syncwarp();
    e_store2d(&mout, ot + hf * 2048, (hp & 3) * 128 + hf * 64, (rt * 4 + (hp >> 2)) * 64 + w * 16);
  };
  float oc[64];
#pragma unroll 1
  for (int j = 0; j < 8; j++) {
    const int kb = (j + 7) & 7;
    if ((j & 1) && j < 6) mbar_spin(BAR(MB_O + 1) + 4 * (j - 1));
    WG_FENCE();
#pragma unroll
    for (int k = 0; k < 4; k++) wgmma_ss_n128(oc, ha | (da0 + 512 * kb + 128 * k), hb | (db0 + 1024 * kb + 128 * k), k ? 1 : j);
    WG_COMMIT();
  }
  WG_WAIT(0);
  TS(10);
  store_half(oc, 0);
  store_half(oc + 32, 1);
  asm volatile(ELECT "cp.async.bulk.commit_group;\n@p cp.async.bulk.wait_group.read 0;\n}\n" ::: "memory");
  TS(wg * 16 + 11);
  GT(61 + wg);
  if (w == 0) TSDUMP(0);
  if (w == 1) TSDUMP(48);
}

typedef CUresult (*EncodeFn)(CUtensorMap*, CUtensorMapDataType, cuuint32_t, void*, const cuuint64_t*, const cuuint64_t*,
                             const cuuint32_t*, const cuuint32_t*, CUtensorMapInterleave, CUtensorMapSwizzle,
                             CUtensorMapL2promotion, CUtensorMapFloatOOBfill);

}

extern "C" void kernel_launch(void* const* d_in, const int* in_sizes, int n_in, void* d_out, int out_size) {
  (void)in_sizes; (void)n_in; (void)out_size;
  void* fn = nullptr;
  cudaDriverEntryPointQueryResult qr;
  cudaGetDriverEntryPoint("cuTensorMapEncodeTiled", &fn, cudaEnableDefault, &qr);
  EncodeFn enc = (EncodeFn)fn;
  CUtensorMap mx, mw, mo, mu, mout, mw4;
  const cuuint32_t es[5] = {1, 1, 1, 1, 1};
  {
    cuuint64_t dims[2] = {512, 2048}, st[1] = {1024};
    cuuint32_t box[2] = {64, 128};
    enc(&mx, CU_TENSOR_MAP_DATA_TYPE_BFLOAT16, 2, d_in[0], dims, st, box, es, CU_TENSOR_MAP_INTERLEAVE_NONE,
        CU_TENSOR_MAP_SWIZZLE_128B, CU_TENSOR_MAP_L2_PROMOTION_L2_128B, CU_TENSOR_MAP_FLOAT_OOB_FILL_NONE);
  }
  {
    cuuint64_t dims[3] = {512, 512, 3}, st[2] = {3072, 1024};
    cuuint32_t box[3] = {32, 64, 3};
    enc(&mw, CU_TENSOR_MAP_DATA_TYPE_BFLOAT16, 3, d_in[1], dims, st, box, es, CU_TENSOR_MAP_INTERLEAVE_NONE,
        CU_TENSOR_MAP_SWIZZLE_64B, CU_TENSOR_MAP_L2_PROMOTION_L2_128B, CU_TENSOR_MAP_FLOAT_OOB_FILL_NONE);
  }
  {
    cuuint64_t dims[3] = {64, 512, 8}, st[2] = {1024, 128};
    cuuint32_t box[3] = {64, 64, 2};
    enc(&mo, CU_TENSOR_MAP_DATA_TYPE_BFLOAT16, 3, d_in[3], dims, st, box, es, CU_TENSOR_MAP_INTERLEAVE_NONE,
        CU_TENSOR_MAP_SWIZZLE_128B, CU_TENSOR_MAP_L2_PROMOTION_L2_128B, CU_TENSOR_MAP_FLOAT_OOB_FILL_NONE);
  }
  {
    cuuint64_t dims[4] = {512, 4, 16, 32}, st[3] = {16384, 1024, 65536};
    cuuint32_t box[4] = {64, 4, 16, 2};
    enc(&mu, CU_TENSOR_MAP_DATA_TYPE_BFLOAT16, 4, d_in[4], dims, st, box, es, CU_TENSOR_MAP_INTERLEAVE_NONE,
        CU_TENSOR_MAP_SWIZZLE_128B, CU_TENSOR_MAP_L2_PROMOTION_L2_128B, CU_TENSOR_MAP_FLOAT_OOB_FILL_NONE);
  }
  {
    cuuint64_t dims[2] = {1024, 2048}, st[1] = {2048};
    cuuint32_t box[2] = {64, 16};
    enc(&mout, CU_TENSOR_MAP_DATA_TYPE_BFLOAT16, 2, d_out, dims, st, box, es, CU_TENSOR_MAP_INTERLEAVE_NONE,
        CU_TENSOR_MAP_SWIZZLE_128B, CU_TENSOR_MAP_L2_PROMOTION_NONE, CU_TENSOR_MAP_FLOAT_OOB_FILL_NONE);
  }
  {
    cuuint64_t dims[4] = {512, 64, 3, 8}, st[3] = {3072, 1024, 64 * 3072};
    cuuint32_t box[4] = {32, 64, 3, 2};
    enc(&mw4, CU_TENSOR_MAP_DATA_TYPE_BFLOAT16, 4, d_in[1], dims, st, box, es, CU_TENSOR_MAP_INTERLEAVE_NONE,
        CU_TENSOR_MAP_SWIZZLE_64B, CU_TENSOR_MAP_L2_PROMOTION_L2_128B, CU_TENSOR_MAP_FLOAT_OOB_FILL_NONE);
  }
  Params P;
  P.x = (const __nv_bfloat16*)d_in[0];
  P.wphi = (const __nv_bfloat16*)d_in[2];
  P.wo = (const __nv_bfloat16*)d_in[3];
  P.logA = (const __nv_bfloat16*)d_in[5];
  P.Aim = (const __nv_bfloat16*)d_in[6];
  P.Cre = (const __nv_bfloat16*)d_in[7];
  P.Cim = (const __nv_bfloat16*)d_in[8];
  P.logdt = (const __nv_bfloat16*)d_in[9];
  P.Dskip = (const __nv_bfloat16*)d_in[10];
  P.out = (__nv_bfloat16*)d_out;
  cudaGetSymbolAddress((void**)&P.xs, g_x);
  P.ts = nullptr;
  cudaFuncSetAttribute(fused_kernel, cudaFuncAttributeMaxDynamicSharedMemorySize, SMEM_BYTES);
  fused_kernel<<<NCTA, NTHREADS, SMEM_BYTES>>>(P, mx, mw, mo, mu, mout, mw4);
}
```

```cpp
#include <cuda_runtime.h>
#include <cuda_bf16.h>
#include <cuda_fp16.h>
#include <cuda.h>
#include <stdint.h>

#define DBG_TS 0

namespace {

constexpr int NTHREADS = 512;
constexpr int NCTA = 128;
constexpr int OFF_W = 0;
constexpr int OFF_X = 98304;
constexpr int OFF_U = OFF_X + 65536;
constexpr int U_CH = 4416, U_ODD = 2240, U_PAD = 128;
constexpr int OFF_STG0 = OFF_U + 18432;
constexpr int SLAB = 3328;
constexpr int OFF_T = OFF_STG0 + 8 * SLAB;
constexpr int T_CH = 5216;
constexpr int T_D = 0;
constexpr int T_5 = 2144;
constexpr int T_3 = T_5 + 384;
constexpr int T_7 = T_5 + 1024;
constexpr int T_9 = T_7 + 320;
constexpr int T_KC = T_9 + 320;
constexpr int T_ST = T_5 - 1024;
constexpr int OFF_PHI = OFF_T + 4 * T_CH;
constexpr int OFF_EYE = OFF_PHI + 1024, OFF_ONE = OFF_EYE + 512;
constexpr int OFF_BAR = OFF_ONE + 256;
constexpr int SMEM_BYTES = OFF_BAR + 512 + 256 * DBG_TS;
constexpr uint32_t SB = 1024;
static_assert(T_KC + 2 * 656 <= T_CH, "table size");
static_assert(SMEM_BYTES <= 232448, "smem");
constexpr int MB_URAW = 0, MB_FULL = 1  , MB_WO = 17, MB_UFULL = 18, MB_O = 19  ,
              MB_EMPTY = 23  , MB_AUX = 39;
__host__ __device__ constexpr uint32_t BAR(int i) { return SB + OFF_BAR + 8 * i; }
constexpr int NB_WG0 = 1, NB_ODONE = 2, NB_ST0 = 3  , NB_KV = 5, NB_YZ = 6, NB_INIT = 7, NB_PREP = 8, NB_PROD = 9, NB_KREAD = 10, NB_BDONE = 11, NB_GATE = 12,
              NB_Y = 7  ;
#define X2_AT -1
#define GATE_B 0
#define U_AT 2
#define ZERO_STEP 12
constexpr int SPIN_MAX = 1 << 16;

constexpr int X_CNT = 0;
constexpr int X_PART = 256;
constexpr int X_O = X_PART + 16 * 8 * 144;
constexpr int X_Y = X_O + 32 * 32 * 128;
constexpr int X_UT = X_Y + 512 * 8 * 32;
constexpr int X_SIZE = X_UT + 512 * (U_CH / 16);
__device__ __align__(128) uint4 g_x[X_SIZE];
extern __shared__ uint8_t smem_raw[];
#define TS(i) do {} while (0)
#define TS1(i) do {} while (0)
#define GT(i) do {} while (0)
#define TSDUMP(base) do {} while (0)

__device__ __forceinline__ uint32_t smem_u32(const void* p) { return (uint32_t)__cvta_generic_to_shared(p); }
__device__ __forceinline__ void mbar_arrive(uint32_t b) {
  asm volatile("mbarrier.arrive.shared::cta.b64 _, [%0];" ::"r"(b) : "memory");
}
__device__ __forceinline__ void mbar_wait(uint32_t b) {
  uint32_t done = 0;
#pragma unroll 1
  for (int i = 0; i < SPIN_MAX && !done; i++) {
    asm volatile("{\n.reg .pred p;\nmbarrier.try_wait.parity.shared::cta.b64 p, [%1], 0, 4000;\nselp.u32 %0, 1, 0, p;\n}\n"
                 : "=r"(done) : "r"(b) : "memory");
  }
}
__device__ __forceinline__ void mbar_spin(uint32_t b) {
  uint32_t done = 0;
#pragma unroll 1
  for (int i = 0; i < (SPIN_MAX << 4) && !done; i++) {
    asm volatile("{\n.reg .pred p;\nmbarrier.try_wait.parity.shared::cta.b64 p, [%1], 0;\nselp.u32 %0, 1, 0, p;\n}\n"
                 : "=r"(done) : "r"(b) : "memory");
  }
}
__device__ __forceinline__ void mbar_init(uint32_t b, int n) {
  asm volatile("mbarrier.init.shared::cta.b64 [%0], %1;" ::"r"(b), "r"(n) : "memory");
}
__device__ __forceinline__ void mbar_expect(uint32_t b, int bytes) {
  asm volatile("mbarrier.arrive.expect_tx.shared::cta.b64 _, [%0], %1;" ::"r"(b), "r"(bytes) : "memory");
}
__device__ __forceinline__ void nb_sync(int id, int n) { asm volatile("bar.sync %0, %1;" ::"r"(id), "r"(n) : "memory"); }
__device__ __forceinline__ void nb_arrive(int id, int n) { asm volatile("bar.arrive %0, %1;" ::"r"(id), "r"(n) : "memory"); }
#define ELECT "{\n.reg .pred p;\nelect.sync _|p, 0xffffffff;\n@p "
__device__ __forceinline__ void e_arrive(uint32_t b) {
  asm volatile(ELECT "mbarrier.arrive.shared::cta.b64 _, [%0];\n}\n" ::"r"(b) : "memory");
}
__device__ __forceinline__ void e_expect(uint32_t b, int bytes) {
  asm volatile(ELECT "mbarrier.arrive.expect_tx.shared::cta.b64 _, [%0], %1;\n}\n" ::"r"(b), "r"(bytes) : "memory");
}
__device__ __forceinline__ void e_tma2d(uint32_t dst, const CUtensorMap* m, uint32_t bar, int c0, int c1) {
  asm volatile(ELECT "cp.async.bulk.tensor.2d.shared::cluster.global.mbarrier::complete_tx::bytes [%0], [%1, {%3,%4}], [%2];\n}\n"
               ::"r"(dst), "l"(m), "r"(bar), "r"(c0), "r"(c1) : "memory");
}
__device__ __forceinline__ void e_tma3d(uint32_t dst, const CUtensorMap* m, uint32_t bar, int c0, int c1, int c2) {
  asm volatile(ELECT "cp.async.bulk.tensor.3d.shared::cluster.global.mbarrier::complete_tx::bytes [%0], [%1, {%3,%4,%5}], [%2];\n}\n"
               ::"r"(dst), "l"(m), "r"(bar), "r"(c0), "r"(c1), "r"(c2) : "memory");
}
__device__ __forceinline__ void e_tma4d(uint32_t dst, const CUtensorMap* m, uint32_t bar, int c0, int c3) {
  asm volatile(ELECT "cp.async.bulk.tensor.4d.shared::cluster.global.mbarrier::complete_tx::bytes [%0], [%1, {%3,%5,%5,%4}], [%2];\n}\n"
               ::"r"(dst), "l"(m), "r"(bar), "r"(c0), "r"(c3), "r"(0) : "memory");
}
__device__ __forceinline__ void e_bulk(uint32_t dst, const void* src, int bytes, uint32_t bar) {
  asm volatile(ELECT "cp.async.bulk.shared::cluster.global.mbarrier::complete_tx::bytes [%0], [%1], %2, [%3];\n}\n"
               ::"r"(dst), "l"(src), "r"(bytes), "r"(bar) : "memory");
}
__device__ __forceinline__ void e_prefetch(const void* p, int bytes) {
  asm volatile(ELECT "cp.async.bulk.prefetch.L2.global [%0], %1;\n}\n" ::"l"(p), "r"(bytes) : "memory");
}
__device__ __forceinline__ void e_store2d(const CUtensorMap* m, uint32_t src, int c0, int c1) {
  asm volatile(ELECT "cp.async.bulk.tensor.2d.global.shared::cta.bulk_group [%0, {%2,%3}], [%1];\n}\n"
               ::"l"(m), "r"(src), "r"(c0), "r"(c1) : "memory");
}
__host__ __device__ constexpr uint64_t mkdesc(uint32_t addr, uint32_t lbo, uint32_t sbo, int swz) {
  return (uint64_t)((addr & 0x3FFFF) >> 4) | ((uint64_t)(lbo >> 4) << 16) | ((uint64_t)(sbo >> 4) << 32) |
         ((uint64_t)swz << 62);
}
#define SPLIT() asm volatile("{\n.reg .pred p;\nsetp.eq.u32 p, %0, %1;\n@p exit;\n}\n" ::"r"(blockIdx.y), "n"(__LINE__) : "memory")
#define WG_FENCE() asm volatile("wgmma.fence.sync.aligned;" ::: "memory")
#define WG_COMMIT() asm volatile("wgmma.commit_group.sync.aligned;" ::: "memory")
#define WG_WAIT(n) asm volatile("wgmma.wait_group.sync.aligned " #n ";" ::: "memory")

__device__ __forceinline__ void mma(float& d0, float& d1, float& d2, float& d3, uint32_t a0, uint32_t a1, uint32_t a2,
                                    uint32_t a3, uint32_t b0, uint32_t b1) {
  asm volatile("mma.sync.aligned.m16n8k16.row.col.f32.bf16.bf16.f32 {%0,%1,%2,%3},{%4,%5,%6,%7},{%8,%9},{%0,%1,%2,%3};"
               : "+f"(d0), "+f"(d1), "+f"(d2), "+f"(d3)
               : "r"(a0), "r"(a1), "r"(a2), "r"(a3), "r"(b0), "r"(b1));
}
__device__ __forceinline__ void mmac(float (&d)[4], uint32_t a0, uint32_t a1, uint32_t a2, uint32_t a3, uint32_t b0,
                                     uint32_t b1, const float (&c)[4]) {
  asm volatile("mma.sync.aligned.m16n8k16.row.col.f32.bf16.bf16.f32 {%0,%1,%2,%3},{%4,%5,%6,%7},{%8,%9},{%10,%11,%12,%13};"
               : "=f"(d[0]), "=f"(d[1]), "=f"(d[2]), "=f"(d[3])
               : "r"(a0), "r"(a1), "r"(a2), "r"(a3), "r"(b0), "r"(b1), "f"(c[0]), "f"(c[1]), "f"(c[2]), "f"(c[3]));
}
__device__ __forceinline__ void mma_p(int p, float (&d)[4], uint32_t a0, uint32_t a1, uint32_t a2, uint32_t a3, uint32_t b0, uint32_t b1) {
  asm volatile("{\n.reg .pred q;\nsetp.ne.b32 q, %10, 0;\n"
               "@q mma.sync.aligned.m16n8k16.row.col.f32.bf16.bf16.f32 {%0,%1,%2,%3},{%4,%5,%6,%7},{%8,%9},{%0,%1,%2,%3};\n}\n"
               : "+f"(d[0]), "+f"(d[1]), "+f"(d[2]), "+f"(d[3])
               : "r"(a0), "r"(a1), "r"(a2), "r"(a3), "r"(b0), "r"(b1), "r"(p));
}
__device__ __forceinline__ void mmac_p(int p, float (&d)[4], uint32_t a0, uint32_t a1, uint32_t a2, uint32_t a3, uint32_t b0,
                                       uint32_t b1, const float (&c)[4]) {
  asm volatile("{\n.reg .pred q;\nsetp.ne.b32 q, %14, 0;\n"
               "@q mma.sync.aligned.m16n8k16.row.col.f32.bf16.bf16.f32 {%0,%1,%2,%3},{%4,%5,%6,%7},{%8,%9},{%10,%11,%12,%13};\n}\n"
               : "+f"(d[0]), "+f"(d[1]), "+f"(d[2]), "+f"(d[3])
               : "r"(a0), "r"(a1), "r"(a2), "r"(a3), "r"(b0), "r"(b1), "f"(c[0]), "f"(c[1]), "f"(c[2]), "f"(c[3]), "r"(p));
}
__device__ __forceinline__ void mma_h(float (&d)[4], const uint32_t (&a)[4], uint32_t b0, uint32_t b1) {
  asm volatile("mma.sync.aligned.m16n8k16.row.col.f32.f16.f16.f32 {%0,%1,%2,%3},{%4,%5,%6,%7},{%8,%9},{%0,%1,%2,%3};"
               : "+f"(d[0]), "+f"(d[1]), "+f"(d[2]), "+f"(d[3]) : "r"(a[0]), "r"(a[1]), "r"(a[2]), "r"(a[3]), "r"(b0), "r"(b1));
}
__device__ __forceinline__ void mma0(float& d0, float& d1, float& d2, float& d3, uint32_t a0, uint32_t a1, uint32_t a2,
                                     uint32_t a3, uint32_t b0, uint32_t b1) {
  asm volatile("mma.sync.aligned.m16n8k16.row.col.f32.bf16.bf16.f32 {%0,%1,%2,%3},{%4,%5,%6,%7},{%8,%9},{%10,%10,%10,%10};"
               : "=f"(d0), "=f"(d1), "=f"(d2), "=f"(d3)
               : "r"(a0), "r"(a1), "r"(a2), "r"(a3), "r"(b0), "r"(b1), "f"(0.f));
}
__device__ __forceinline__ uint32_t pack_bf(float lo, float hi) {
  uint32_t r;
  asm("cvt.rn.bf16x2.f32 %0, %1, %2;" : "=r"(r) : "f"(hi), "f"(lo));
  return r;
}
__device__ __forceinline__ float bf_lo(uint32_t w) { return __uint_as_float(w << 16); }
__device__ __forceinline__ float bf_hi(uint32_t w) { return __uint_as_float(w & 0xffff0000u); }
__device__ __forceinline__ float bf_round(float x) { return __bfloat162float(__float2bfloat16_rn(x)); }
__device__ __forceinline__ uint32_t bmax2(uint32_t a, uint32_t b) {
  uint32_t r; asm("max.bf16x2 %0, %1, %2;" : "=r"(r) : "r"(a), "r"(b)); return r;
}
__device__ __forceinline__ uint32_t bmin2(uint32_t a, uint32_t b) {
  uint32_t r; asm("min.bf16x2 %0, %1, %2;" : "=r"(r) : "r"(a), "r"(b)); return r;
}
__device__ __forceinline__ float ex2(float x) { float r; asm("ex2.approx.ftz.f32 %0, %1;" : "=f"(r) : "f"(x)); return r; }
__device__ __forceinline__ float rcp(float x) { float r; asm("rcp.approx.ftz.f32 %0, %1;" : "=f"(r) : "f"(x)); return r; }
__device__ __forceinline__ void ldsm4(uint32_t (&r)[4], uint32_t a) {
  asm volatile("ldmatrix.sync.aligned.m8n8.x4.shared.b16 {%0,%1,%2,%3}, [%4];"
               : "=r"(r[0]), "=r"(r[1]), "=r"(r[2]), "=r"(r[3]) : "r"(a) : "memory");
}
__device__ __forceinline__ void ldsm4t(uint32_t (&r)[4], uint32_t a) {
  asm volatile("ldmatrix.sync.aligned.m8n8.x4.trans.shared.b16 {%0,%1,%2,%3}, [%4];"
               : "=r"(r[0]), "=r"(r[1]), "=r"(r[2]), "=r"(r[3]) : "r"(a) : "memory");
}
__device__ __forceinline__ void stsm4(uint32_t a, uint32_t r0, uint32_t r1, uint32_t r2, uint32_t r3) {
  asm volatile("stmatrix.sync.aligned.m8n8.x4.shared.b16 [%0], {%1,%2,%3,%4};"
               ::"r"(a), "r"(r0), "r"(r1), "r"(r2), "r"(r3) : "memory");
}
__device__ __forceinline__ uint32_t lds32(uint32_t a) {
  uint32_t r; asm volatile("ld.shared.u32 %0, [%1];" : "=r"(r) : "r"(a) : "memory"); return r;
}
__device__ __forceinline__ uint32_t lds16(uint32_t a) {
  uint32_t r; asm volatile("{\n.reg .u16 h;\nld.shared.u16 h, [%1];\ncvt.u32.u16 %0, h;\n}\n" : "=r"(r) : "r"(a) : "memory"); return r;
}
__device__ __forceinline__ uint2 lds64(uint32_t a) {
  uint2 r; asm volatile("ld.shared.v2.u32 {%0,%1}, [%2];" : "=r"(r.x), "=r"(r.y) : "r"(a) : "memory"); return r;
}
__device__ __forceinline__ uint4 lds128(uint32_t a) {
  uint4 r;
  asm volatile("ld.shared.v4.u32 {%0,%1,%2,%3}, [%4];" : "=r"(r.x), "=r"(r.y), "=r"(r.z), "=r"(r.w) : "r"(a) : "memory");
  return r;
}
__device__ __forceinline__ void sts32(uint32_t a, uint32_t v) { asm volatile("st.shared.u32 [%0], %1;" ::"r"(a), "r"(v) : "memory"); }
__device__ __forceinline__ void sts16(uint32_t a, uint32_t v) {
  asm volatile("{\n.reg .u16 h;\ncvt.u16.u32 h, %1;\nst.shared.u16 [%0], h;\n}\n" ::"r"(a), "r"(v) : "memory");
}
__device__ __forceinline__ void sts64(uint32_t a, uint32_t x, uint32_t y) {
  asm volatile("st.shared.v2.u32 [%0], {%1,%2};" ::"r"(a), "r"(x), "r"(y) : "memory");
}
__device__ __forceinline__ void sts128(uint32_t a, uint32_t x, uint32_t y, uint32_t z, uint32_t w) {
  asm volatile("st.shared.v4.u32 [%0], {%1,%2,%3,%4};" ::"r"(a), "r"(x), "r"(y), "r"(z), "r"(w) : "memory");
}
__device__ __forceinline__ uint4 ld_x(const uint4* p) {
  uint4 r;
  asm volatile("{\n.reg .b128 t;\nld.relaxed.gpu.global.b128 t, [%4];\nmov.b128 {%0,%1,%2,%3}, t;\n}\n"
               : "=r"(r.x), "=r"(r.y), "=r"(r.z), "=r"(r.w) : "l"(p) : "memory");
  return r;
}
__device__ __forceinline__ uint32_t ld_x32(const uint32_t* p) {
  uint32_t r; asm volatile("ld.relaxed.gpu.global.u32 %0, [%1];" : "=r"(r) : "l"(p) : "memory"); return r;
}
__device__ __forceinline__ void st_x(uint4* p, uint32_t x, uint32_t y, uint32_t z, uint32_t w) {
  asm volatile("{\n.reg .b128 t;\nmov.b128 t, {%1,%2,%3,%4};\nst.relaxed.gpu.global.b128 [%0], t;\n}\n"
               ::"l"(p), "r"(x), "r"(y), "r"(z), "r"(w) : "memory");
}
__device__ __forceinline__ void st_x_p(int p, uint4* a, uint32_t x, uint32_t y, uint32_t z, uint32_t w) {
  asm volatile("{\n.reg .b128 t;\n.reg .pred q;\nsetp.ne.b32 q, %5, 0;\nmov.b128 t, {%1,%2,%3,%4};\n@q st.relaxed.gpu.global.b128 [%0], t;\n}\n"
               ::"l"(a), "r"(x), "r"(y), "r"(z), "r"(w), "r"(p) : "memory");
}
__device__ __forceinline__ void sts64_p(int p, uint32_t a, uint32_t x, uint32_t y) {
  asm volatile("{\n.reg .pred q;\nsetp.ne.b32 q, %3, 0;\n@q st.shared.v2.u32 [%0], {%1,%2};\n}\n" ::"r"(a), "r"(x), "r"(y), "r"(p) : "memory");
}
__device__ __forceinline__ void st_x32(uint32_t* p, uint32_t x) {
  asm volatile("st.relaxed.gpu.global.u32 [%0], %1;" ::"l"(p), "r"(x) : "memory");
}
__device__ __forceinline__ uint32_t nz(uint32_t w) { return max(w, 1u); }
__device__ __forceinline__ uint32_t fu(float x) { return __float_as_uint(x); }
__device__ __forceinline__ float uf(uint32_t x) { return __uint_as_float(x); }

__device__ __forceinline__ void wgmma_ss_n96(float (&d)[48], uint64_t da, uint64_t db, int sc) {
  asm volatile("{\n.reg .pred p;\nsetp.ne.b32 p, %50, 0;\n"
      "wgmma.mma_async.sync.aligned.m64n96k16.f32.bf16.bf16 "
      "{%0,%1,%2,%3,%4,%5,%6,%7,%8,%9,%10,%11,%12,%13,%14,%15,%16,%17,%18,%19,%20,%21,%22,%23,%24,%25,%26,%27,%28,%29,%30,%31,%32,%33,%34,%35,%36,%37,%38,%39,%40,%41,%42,%43,%44,%45,%46,%47}, "
      "%48, %49, p, 1, 1, 0, 1;\n}\n"
      : "+f"(d[0]), "+f"(d[1]), "+f"(d[2]), "+f"(d[3]), "+f"(d[4]), "+f"(d[5]), "+f"(d[6]), "+f"(d[7]),
        "+f"(d[8]), "+f"(d[9]), "+f"(d[10]), "+f"(d[11]), "+f"(d[12]), "+f"(d[13]), "+f"(d[14]), "+f"(d[15]),
        "+f"(d[16]), "+f"(d[17]), "+f"(d[18]), "+f"(d[19]), "+f"(d[20]), "+f"(d[21]), "+f"(d[22]), "+f"(d[23]),
        "+f"(d[24]), "+f"(d[25]), "+f"(d[26]), "+f"(d[27]), "+f"(d[28]), "+f"(d[29]), "+f"(d[30]), "+f"(d[31]),
        "+f"(d[32]), "+f"(d[33]), "+f"(d[34]), "+f"(d[35]), "+f"(d[36]), "+f"(d[37]), "+f"(d[38]), "+f"(d[39]),
        "+f"(d[40]), "+f"(d[41]), "+f"(d[42]), "+f"(d[43]), "+f"(d[44]), "+f"(d[45]), "+f"(d[46]), "+f"(d[47])
      : "l"(da), "l"(db), "r"(sc));
}

__device__ __forceinline__ void wgmma_ss_n128(float (&d)[64], uint64_t da, uint64_t db, int sc) {
  asm volatile("{\n.reg .pred p;\nsetp.ne.b32 p, %66, 0;\n"
      "wgmma.mma_async.sync.aligned.m64n128k16.f32.bf16.bf16 "
      "{%0,%1,%2,%3,%4,%5,%6,%7,%8,%9,%10,%11,%12,%13,%14,%15,%16,%17,%18,%19,%20,%21,%22,%23,%24,%25,%26,%27,%28,%29,%30,%31,%32,%33,%34,%35,%36,%37,%38,%39,%40,%41,%42,%43,%44,%45,%46,%47,%48,%49,%50,%51,%52,%53,%54,%55,%56,%57,%58,%59,%60,%61,%62,%63}, "
      "%64, %65, p, 1, 1, 0, 1;\n}\n"
      : "+f"(d[0]), "+f"(d[1]), "+f"(d[2]), "+f"(d[3]), "+f"(d[4]), "+f"(d[5]), "+f"(d[6]), "+f"(d[7]),
        "+f"(d[8]), "+f"(d[9]), "+f"(d[10]), "+f"(d[11]), "+f"(d[12]), "+f"(d[13]), "+f"(d[14]), "+f"(d[15]),
        "+f"(d[16]), "+f"(d[17]), "+f"(d[18]), "+f"(d[19]), "+f"(d[20]), "+f"(d[21]), "+f"(d[22]), "+f"(d[23]),
        "+f"(d[24]), "+f"(d[25]), "+f"(d[26]), "+f"(d[27]), "+f"(d[28]), "+f"(d[29]), "+f"(d[30]), "+f"(d[31]),
        "+f"(d[32]), "+f"(d[33]), "+f"(d[34]), "+f"(d[35]), "+f"(d[36]), "+f"(d[37]), "+f"(d[38]), "+f"(d[39]),
        "+f"(d[40]), "+f"(d[41]), "+f"(d[42]), "+f"(d[43]), "+f"(d[44]), "+f"(d[45]), "+f"(d[46]), "+f"(d[47]),
        "+f"(d[48]), "+f"(d[49]), "+f"(d[50]), "+f"(d[51]), "+f"(d[52]), "+f"(d[53]), "+f"(d[54]), "+f"(d[55]),
        "+f"(d[56]), "+f"(d[57]), "+f"(d[58]), "+f"(d[59]), "+f"(d[60]), "+f"(d[61]), "+f"(d[62]), "+f"(d[63])
      : "l"(da), "l"(db), "r"(sc));
}

__device__ __forceinline__ void wgmma_ss_n40(float (&d)[20], uint64_t da, uint64_t db, int sc) {
  asm volatile("{\n.reg .pred p;\nsetp.ne.b32 p, %22, 0;\n"
      "wgmma.mma_async.sync.aligned.m64n40k16.f32.bf16.bf16 "
      "{%0,%1,%2,%3,%4,%5,%6,%7,%8,%9,%10,%11,%12,%13,%14,%15,%16,%17,%18,%19}, "
      "%20, %21, p, 1, 1, 1, 1;\n}\n"
      : "+f"(d[0]), "+f"(d[1]), "+f"(d[2]), "+f"(d[3]), "+f"(d[4]), "+f"(d[5]), "+f"(d[6]), "+f"(d[7]),
        "+f"(d[8]), "+f"(d[9]), "+f"(d[10]), "+f"(d[11]), "+f"(d[12]), "+f"(d[13]), "+f"(d[14]), "+f"(d[15]),
        "+f"(d[16]), "+f"(d[17]), "+f"(d[18]), "+f"(d[19])
      : "l"(da), "l"(db), "r"(sc));
}

__device__ __forceinline__ void wgmma_rs_n8(float (&d)[4], const uint4& a, uint64_t db, int sc) {
  asm volatile("{\n.reg .pred p;\nsetp.ne.b32 p, %9, 0;\n"
      "wgmma.mma_async.sync.aligned.m64n8k16.f32.bf16.bf16 "
      "{%0,%1,%2,%3}, "
      "{%4,%5,%6,%7}, %8, p, 1, 1, 1;\n}\n"
      : "+f"(d[0]), "+f"(d[1]), "+f"(d[2]), "+f"(d[3])
      : "r"(a.x), "r"(a.y), "r"(a.z), "r"(a.w), "l"(db), "r"(sc));
}

__device__ __forceinline__ void wgmma_rs_n16(float (&d)[8], const uint4& a, uint64_t db, int sc) {
  asm volatile("{\n.reg .pred p;\nsetp.ne.b32 p, %13, 0;\n"
      "wgmma.mma_async.sync.aligned.m64n16k16.f32.bf16.bf16 "
      "{%0,%1,%2,%3,%4,%5,%6,%7}, "
      "{%8,%9,%10,%11}, %12, p, 1, 1, 1;\n}\n"
      : "+f"(d[0]), "+f"(d[1]), "+f"(d[2]), "+f"(d[3]), "+f"(d[4]), "+f"(d[5]), "+f"(d[6]), "+f"(d[7])
      : "r"(a.x), "r"(a.y), "r"(a.z), "r"(a.w), "l"(db), "r"(sc));
}

__device__ __forceinline__ void wgmma_rs_n24(float (&d)[12], const uint4& a, uint64_t db, int sc) {
  asm volatile("{\n.reg .pred p;\nsetp.ne.b32 p, %17, 0;\n"
      "wgmma.mma_async.sync.aligned.m64n24k16.f32.bf16.bf16 "
      "{%0,%1,%2,%3,%4,%5,%6,%7,%8,%9,%10,%11}, "
      "{%12,%13,%14,%15}, %16, p, 1, 1, 1;\n}\n"
      : "+f"(d[0]), "+f"(d[1]), "+f"(d[2]), "+f"(d[3]), "+f"(d[4]), "+f"(d[5]), "+f"(d[6]), "+f"(d[7]),
        "+f"(d[8]), "+f"(d[9]), "+f"(d[10]), "+f"(d[11])
      : "r"(a.x), "r"(a.y), "r"(a.z), "r"(a.w), "l"(db), "r"(sc));
}

struct Params {
  const __nv_bfloat16 *logA, *Aim, *Cre, *Cim, *logdt, *Dskip, *x, *wphi, *wo;
  __nv_bfloat16* out;
  uint4* xs;
  long long* ts;
};

__device__ __forceinline__ uint4 tr_row(const uint4 (&v)[8], int i) {
  uint32_t o[4];
#pragma unroll
  for (int m = 0; m < 4; m++) {
    const uint4 &ra = v[2 * m], &rb = v[2 * m + 1];
    const int k = i >> 1;
    const uint32_t xa = k == 0 ? ra.x : k == 1 ? ra.y : k == 2 ? ra.z : ra.w;
    const uint32_t xb = k == 0 ? rb.x : k == 1 ? rb.y : k == 2 ? rb.z : rb.w;
    o[m] = __byte_perm(xa, xb, (i & 1) ? 0x7632 : 0x5410);
  }
  return make_uint4(o[0], o[1], o[2], o[3]);
}

struct cpx { float r, i; };
__device__ __forceinline__ cpx csq(cpx a) { return {a.r * a.r - a.i * a.i, 2.f * (a.r * a.i)}; }
__device__ __forceinline__ cpx polar(float e, float t) {
  const float m = ex2(e);
  return {m * __cosf(t), m * __sinf(t)};
}

struct KgenRaw { unsigned short la, ai, cr, ci, ldt; };
__device__ __forceinline__ KgenRaw kgen_load(const Params& P, int d, int unit, int lane) {
  const int o = d * 128 + unit * 32 + lane;
  return {__ldg((const unsigned short*)P.logA + o), __ldg((const unsigned short*)P.Aim + o), __ldg((const unsigned short*)P.Cre + o),
          __ldg((const unsigned short*)P.Cim + o), __ldg((const unsigned short*)P.logdt + d)};
}
struct hmul { __half2 a, b; };
__device__ __forceinline__ hmul mk_mul(cpx w) {
  uint32_t b;
  asm("{\n.reg .f32 n;\nneg.ftz.f32 n, %1;\ncvt.rn.f16x2.f32 %0, %2, n;\n}\n" : "=r"(b) : "f"(w.i), "f"(w.r));
  return {__floats2half2_rn(w.r, w.i), *(const __half2*)&b};
}
__device__ __forceinline__ __half2 hcm(__half2 z, const hmul& w) { return __hfma2(__high2half2(z), w.b, __hmul2(__low2half2(z), w.a)); }
__device__ __forceinline__ uint32_t hu(__half2 v) { return *(const uint32_t*)&v; }

struct KgenAddr { uint32_t sa, lb, lm[4]; };
__device__ __forceinline__ KgenAddr kgen_addr(int lane, uint32_t buf) {
  KgenAddr a;
  a.sa = buf + (lane & 7) * 128 + ((((lane >> 3) ^ lane) & 7) << 4);
  const int q = lane >> 3;
  a.lb = buf + q * 128 + (((lane ^ q) & 7) << 4);
  a.lm[0] = buf + q * 128 + (q << 4);
  a.lm[1] = buf + q * 128 + ((1 ^ q) << 4);
  a.lm[2] = buf + q * 128 + (((2 + (lane & 1)) ^ q) << 4);
  a.lm[3] = buf + q * 128 + (((4 + (lane & 3)) ^ q) << 4);
  asm volatile("" : "+r"(a.sa), "+r"(a.lb), "+r"(a.lm[0]), "+r"(a.lm[1]), "+r"(a.lm[2]), "+r"(a.lm[3]));
  return a;
}
__device__ __forceinline__ void kgen_unit(const KgenRaw& r, const KgenAddr& ad, uint32_t zero, float (&k)[5][4], float& k2048, float& sc) {
  const float dt = bf_round(expf(bf_lo(r.ldt)));
  const float a2 = bf_round(ex2(bf_lo(r.la) * 1.4426950408889634f)) * (dt * -1.4426950408889634f);
  const float f = bf_lo(r.ai) * dt;
  const float r127 = f * 20.21267777267071f;
  const uint32_t ex = min(max(__reduce_max_sync(0xffffffffu, max(r.cr & 0x7fffu, r.ci & 0x7fffu)) >> 7, 1u), 253u);
  const float cs = uf((254u - ex) << 23);
  sc = 2.f * dt * uf(ex << 23);
  const cpx C = {bf_lo(r.cr) * cs, -bf_lo(r.ci) * cs};
  auto put = [&](const __half2 (&v)[8]) {
    stsm4(ad.sa, hu(v[0]), hu(v[1]), hu(v[2]), hu(v[3]));
    stsm4(ad.sa ^ 64, hu(v[4]), hu(v[5]), hu(v[6]), hu(v[7]));
    __syncwarp();
  };
  auto get = [&](uint32_t (&o)[2][4], uint32_t a) { ldsm4(o[0], a); ldsm4(o[1], (a ^ 64) + 512); };
  auto rot = [](uint32_t z) { return __byte_perm(z, z, 0x1032) ^ 0x8000u; };
  auto fmul = [](uint32_t z, uint32_t zi, uint32_t w) {
    const __half2 hw = *(const __half2*)&w;
    return hu(__hfma2(*(const __half2*)&zi, __high2half2(hw), __hmul2(*(const __half2*)&z, __low2half2(hw))));
  };
  uint32_t A[4][4];
  auto tile = [&](int j, const uint32_t (&B)[2][4]) {
    k[j][0] = k[j][1] = k[j][2] = k[j][3] = 0.f;
#pragma unroll
    for (int s = 0; s < 4; s++) mma_h(k[j], A[s], B[s >> 1][2 * (s & 1)], B[s >> 1][2 * (s & 1) + 1]);
  };
  auto after = [&](cpx v, uint32_t dep) { return cpx{uf(fu(v.r) ^ (dep & zero)), v.i}; };
  const cpx w1 = polar(a2, f), w127 = polar(a2 * 127.f, (r127 - rintf(r127)) * 6.283185307179586f);
  const cpx w2 = csq(w1), w4 = csq(w2);
  uint32_t T0[2][4], A0[2][4], T4[2][4], M[4][2][4];
  {
    __half2 t[8];
    const hmul m2 = mk_mul(w2), m4 = mk_mul(w4);
    t[0] = __floats2half2_rn(1.f, 0.f); t[1] = __floats2half2_rn(w1.r, w1.i); t[2] = m2.a; t[4] = m4.a;
    t[3] = hcm(t[1], m2); t[5] = hcm(t[1], m4); t[6] = hcm(t[2], m4); t[7] = hcm(t[3], m4);
    put(t); get(T0, ad.lb);
  }
  cpx w8 = csq(w4);
  w8.i = -w8.i;
  const cpx w16 = csq(w8), w32 = csq(w16), w64 = csq(w32);
  {
    const hmul m8 = mk_mul(w8), m16 = mk_mul(w16), m32 = mk_mul(w32);
    __half2 a[8];
    a[0] = __floats2half2_rn(C.r, C.i); a[1] = hcm(a[0], m8);
    a[2] = hcm(a[0], m16); a[3] = hcm(a[1], m16);
#pragma unroll
    for (int i = 0; i < 4; i++) a[4 + i] = hcm(a[i], m32);
    put(a); get(A0, ad.lb);
  }
  const cpx w127b = after(w127, T0[0][0]);
  const cpx w128 = {w127b.r * w1.r - w127b.i * w1.i, w127b.r * w1.i + w127b.i * w1.r};
  const cpx w256 = csq(w128), w512 = csq(w256);
  const hmul m128 = mk_mul(w128), m256 = mk_mul(w256), m512 = mk_mul(w512);
  {
    const hmul m254 = mk_mul(csq(w127b));
    const __half2 h127 = __floats2half2_rn(w127b.r, w127b.i);
    __half2 m[8];
    m[0] = __floats2half2_rn(w64.r, w64.i); m[1] = m128.a; m[2] = m256.a; m[3] = hcm(h127, m256);
    m[4] = m512.a; m[5] = hcm(h127, m512); m[6] = hcm(m[4], m254); m[7] = hcm(m[5], m254);
    put(m);
#pragma unroll
    for (int i = 0; i < 4; i++) get(M[i], ad.lm[i]);
  }
  const cpx w1024 = csq(after(w512, A0[0][0])), we = csq(w1024);
  {
    __half2 t[8];
    t[0] = __floats2half2_rn(w1024.r, w1024.i); t[1] = hcm(t[0], m128);
    t[2] = hcm(t[0], m256); t[3] = hcm(t[1], m256);
#pragma unroll
    for (int i = 0; i < 4; i++) t[4 + i] = hcm(t[i], m512);
    put(t); get(T4, ad.lb);
  }
  k2048 = (C.r * we.r + C.i * we.i) * sc;
#pragma unroll
  for (int i = 0; i < 8; i++) {
    const uint32_t z = A0[i >> 2][i & 3];
    A[i >> 1][2 * (i & 1)] = z;
    A[i >> 1][2 * (i & 1) + 1] = fmul(z, rot(z), M[0][i >> 2][i & 3]);
  }
  tile(0, T0);
#pragma unroll
  for (int i = 0; i < 8; i++) {
    const uint32_t z = T0[i >> 2][i & 3], zi = rot(z);
#pragma unroll
    for (int j = 1; j < 4; j++) M[j][i >> 2][i & 3] = fmul(z, zi, M[j][i >> 2][i & 3]);
  }
  tile(4, T4); tile(1, M[1]); tile(2, M[2]); tile(3, M[3]);
}

__device__ __forceinline__ void build_tables(uint32_t tb, int lane, float (&k)[5][4], float k2048) {
  const int g = lane >> 2, c = lane & 3;
  const uint32_t kc = tb + T_KC + 16;
  {
    const uint32_t a0 = kc + 16 * g + 4 * c, a2 = kc + 2 * (256 + 4 * g + c);
    const uint32_t a3 = kc + 2 * (384 + 2 * g + 64 * (c & 1) + (c >> 1)), a4 = kc + 2 * (512 + g + 32 * c);
#pragma unroll
    for (int r = 0; r < 2; r++) {
      sts32(a0 + 128 * r, pack_bf(k[0][2 * r], k[0][2 * r + 1]));
      sts32(a0 + 128 * r + 256, pack_bf(k[1][2 * r], k[1][2 * r + 1]));
      const uint32_t w2 = pack_bf(k[2][2 * r], k[2][2 * r + 1]);
      const uint32_t w3 = pack_bf(k[3][2 * r], k[3][2 * r + 1]);
      const uint32_t w4 = pack_bf(k[4][2 * r], k[4][2 * r + 1]);
      sts16(a2 + 64 * r, w2); sts16(a2 + 64 * r + 128, w2 >> 16);
      sts16(a3 + 32 * r, w3); sts16(a3 + 32 * r + 64, w3 >> 16);
      sts16(a4 + 16 * r, w4); sts16(a4 + 16 * r + 32, w4 >> 16);
    }
  }
  if (lane == 0) { sts16(kc + 2 * 640, pack_bf(k2048, 0.f)); sts32(kc - 4, 0); }
  __syncwarp();
  const uint32_t td = tb + T_D + 32;
#pragma unroll
  for (int hf = 0; hf < 2; hf++) {
    const uint2 v = lds64(kc + 256 * hf + 8 * lane);
    const uint32_t pv = lds32(kc + 256 * hf + 8 * lane - 4);
    sts128(td + 512 * hf + 16 * lane, __byte_perm(v.x, pv, 0x7610), __byte_perm(v.x, v.x, 0x1032), __byte_perm(v.y, v.x, 0x7610),
           __byte_perm(v.y, v.y, 0x1032));
  }
#pragma unroll
  for (int hf = 0; hf < 2; hf++) {
    const uint32_t v = lds32(kc + 512 + 128 * hf + 4 * lane), nx = lds32(kc + 516 + 128 * hf + 4 * lane);
    uint32_t w0 = __byte_perm(v, v, 0x1010);
    const uint32_t w1 = w0;
    if (hf == 0) { const uint32_t pv = lds32(kc + 508); if (lane == 0) w0 = __byte_perm(v, pv, 0x7610); }
    sts128(td + 1024 + 512 * hf + 16 * lane, w0, w1, __byte_perm(v, v, 0x1032), __byte_perm(nx, v, 0x7610));
  }
  {
    const uint32_t kk = lds16(kc + 2 * 384);
    const uint32_t w = lane < 3 ? (kk | (kk << 16)) : (lane == 3 ? (kk << 16) : 0u);
    if (lane < 24) sts32(td + 4 * (lane < 16 ? 512 + lane : lane - 24), w);
    const uint32_t lo_ = lds16(kc + 2 * 511), le_ = lds16(kc + 2 * 512);
    const uint32_t ja = tb + T_5 + (lane < 16 ? 4 * lane : 256 + 4 * lane);
    sts32(ja, lane == 16 ? (le_ << 16) : 0u);
    sts32(ja + 384, lane == 16 ? (lo_ << 16) : 0u);
    sts32(tb + (lane < 16 ? T_7 : T_9 - 64) + 4 * lane, 0u);
  }
#pragma unroll
  for (int s = 0; s < 2; s++) {
    const uint32_t b = kc + 2 * (s ? 512 : 384) + 8 * lane;
    const uint2 v = lds64(b);
    uint32_t em = lds16(b - 2), e0 = v.x;
    const uint32_t e4 = lds16(b + 8);
    if (lane == 0) { em = 0; e0 = 0; }
    sts64(tb + (s ? T_7 : T_3) + 64 + 8 * lane, __byte_perm(v.x, em, 0x5432), __byte_perm(v.y, v.x, 0x7632));
    sts64(tb + (s ? T_9 : T_5) + 64 + 8 * lane, __byte_perm(v.y, e0, 0x5410), __byte_perm(e4, v.y, 0x5410));
  }
  __syncwarp();
}

__device__ __forceinline__ uint32_t box2w(int lo, int n, int o) {
  return ((unsigned)(o - lo) < (unsigned)n ? 0x3F80u : 0u) | ((unsigned)(o + 1 - lo) < (unsigned)n ? 0x3F800000u : 0u);
}

__device__ __forceinline__ void conv_channel(uint32_t ub, uint32_t tb, int lane, uint4* ydst) {
  const int g = lane >> 2, c = lane & 3, x = g - 2 * c;
  const int mi = lane >> 3;
  const uint32_t qa = ub + U_PAD + 16 * (lane & 7) + ((mi == 0 || mi == 3) ? U_ODD : 0) - (mi == 0 ? 16 : 0);
  const uint32_t hb = ub + U_PAD + (mi & 1) * U_ODD + 16 * ((lane >> 4) + (lane & 7)) - 16;
  const uint32_t kv = lds16(tb + T_KC + 16 + 2 * 512);
  const int oh = c < 2 ? 8 + 2 * c : 2 * c - 8, og = c < 3 ? 2 * c : -10;
  uint32_t bx[4] = {box2w(g - 4, 9, 2 * c), box2w(g - 3, 7, 2 * c), box2w(g - 4, 9, oh), box2w(g - 3, 7, oh)};
  uint32_t by[4] = {box2w(g - 10, 5, 2 * c - 8), box2w(g - 5, 3, 2 * c - 8), box2w(g - 10, 5, og), box2w(g - 5, 3, og)};
  uint32_t lb0 = ((unsigned)(x + 5) < 2u ? kv : 0u) | ((unsigned)(x + 4) < 2u ? kv << 16 : 0u);
  uint32_t lb1 = ((unsigned)(x - 3) < 2u ? kv : 0u) | ((unsigned)(x - 4) < 2u ? kv << 16 : 0u);
  const int q0 = g - 1, q1 = c < 3 ? g : g - 2;
  uint32_t y0a = ub + U_PAD + (q0 & 1) * U_ODD + 16 * (q0 >> 1) + 4 * c;
  uint32_t y1a = ub + U_PAD + (q1 & 1) * U_ODD + 16 * (q1 >> 1) + 4 * c;
#pragma unroll
  for (int i = 0; i < 4; i++) asm volatile("" : "+r"(bx[i]), "+r"(by[i]));
  asm volatile("" : "+r"(lb0), "+r"(lb1), "+r"(y0a), "+r"(y1a));
  mbar_wait(BAR(MB_UFULL));
  mbar_spin(BAR(MB_EMPTY + 15));
  TS(36);
  float acc[16][4];
  {
    uint32_t z09[8], z07[8], zm9[8], zm7[8];
#pragma unroll
    for (int i = 0; i < 8; i++) {
      uint32_t h[4];
      ldsm4(h, hb + 128 * i);
      float y0, y1, y2, y3, w0, w1, w2, w3;
      mma0(y0, y1, y2, y3, bx[0], bx[1], bx[2], bx[3], h[2], c < 2 ? h[3] : h[1]);
      mma0(w0, w1, w2, w3, bx[0], bx[1], bx[2], bx[3], h[1], c < 2 ? h[2] : h[0]);
      z09[i] = pack_bf(y0, y1); z07[i] = pack_bf(y2, y3);
      zm9[i] = pack_bf(w0, w1); zm7[i] = pack_bf(w2, w3);
    }
  uint32_t f3[3][4][4];
  {
    const uint32_t fa = tb + T_7 + 4 * (16 + x);
#pragma unroll
    for (int tt = 0; tt < 3; tt++)
#pragma unroll
      for (int D = 0; D < 4; D++) {
        const uint32_t a = fa + (tt == 0 ? 316 : (tt == 1 ? 320 : 0)) + 64 * D;
        f3[tt][D][0] = lds32(a); f3[tt][D][1] = lds32(a + 32); f3[tt][D][2] = lds32(a - 32); f3[tt][D][3] = lds32(a);
      }
  }
    float a[4][2][4];
#pragma unroll
    for (int kap = 0; kap < 4; kap++)
#pragma unroll
      for (int sg = 0; sg < 2; sg++)
#pragma unroll
        for (int bk = 3; bk >= kap; bk--) {
          const uint32_t(&q0_)[4] = f3[sg ? 2 : 0][bk - kap];
          const uint32_t(&q1_)[4] = f3[sg ? 2 : 1][bk - kap];
          float(&a0)[4] = a[bk][0];
          float(&a1)[4] = a[bk][1];
          if (sg == 0 && kap == 0) {
            mma0(a0[0], a0[1], a0[2], a0[3], q0_[0], q0_[1], q0_[2], q0_[3], z09[0], z09[1]);
            mma0(a1[0], a1[1], a1[2], a1[3], q1_[0], q1_[1], q1_[2], q1_[3], zm9[0], zm9[1]);
          } else {
            mma(a0[0], a0[1], a0[2], a0[3], q0_[0], q0_[1], q0_[2], q0_[3], sg ? zm7[2 * kap] : z09[2 * kap], sg ? zm7[2 * kap + 1] : z09[2 * kap + 1]);
            mma(a1[0], a1[1], a1[2], a1[3], q1_[0], q1_[1], q1_[2], q1_[3], sg ? z07[2 * kap] : zm9[2 * kap], sg ? z07[2 * kap + 1] : zm9[2 * kap + 1]);
          }
        }
    SPLIT();
#pragma unroll
    for (int i = 0; i < 8; i++) {
      uint32_t h[4];
      ldsm4(h, qa + 128 * i);
      const float ci[4] = {a[i >> 1][0][2 * (i & 1)], a[i >> 1][0][2 * (i & 1) + 1], a[i >> 1][1][2 * (i & 1)], a[i >> 1][1][2 * (i & 1) + 1]};
      mmac(acc[8 + i], h[0], h[1], h[2], h[3], lb0, lb1, ci);
    }
  }
  TS(44);
  {
    uint2 a5[10], a3[10];
    const uint32_t aa = tb + T_5 + 4 * (8 + 2 * g - 2 * c);
#pragma unroll
    for (int m = 0; m < 10; m++) { a5[m] = lds64(aa + 32 * m); a3[m] = lds64(aa + 384 + 32 * m); }
    uint32_t x5[12][2], x3[12][2];
    auto ygen = [&](int kap) {
#pragma unroll
      for (int hh = 0; hh < 2; hh++) {
        float y0, y1, y2, y3;
        mma0(y0, y1, y2, y3, by[0], by[1], by[2], by[3], lds32(y0a + 128 * kap + 64 * hh), lds32(y1a + 128 * kap + 64 * hh));
        x5[kap][hh] = pack_bf(y0, y1);
        x3[kap][hh] = pack_bf(y2, y3);
      }
    };
    ygen(11); ygen(10); ygen(9); ygen(8);
#pragma unroll
    for (int kap = 11; kap >= 0; kap--) {
      if (kap >= 4) ygen(kap - 4);
#pragma unroll
      for (int sg = 0; sg < 2; sg++)
#pragma unroll
        for (int i = 4; i >= 0; i--) {
          const int be = kap + 4 + i;
          if (be <= 15) {
            const uint2 &hi = sg ? a3[2 * i + 1] : a5[2 * i + 1], &lo = sg ? a3[2 * i] : a5[2 * i];
            const uint32_t b0 = sg ? x3[kap][0] : x5[kap][0], b1 = sg ? x3[kap][1] : x5[kap][1];
            if (be < 8 && i == 0 && sg == 0) mma0(acc[be][0], acc[be][1], acc[be][2], acc[be][3], hi.x, hi.y, lo.x, lo.y, b0, b1);
            else mma(acc[be][0], acc[be][1], acc[be][2], acc[be][3], hi.x, hi.y, lo.x, lo.y, b0, b1);
          }
        }
    }
  }
  TS(45);
  {
    const uint32_t st = tb + T_ST + lane * 8;
#pragma unroll
    for (int be = 4; be < 12; be++) sts64(st + 256 * be, pack_bf(acc[be][0], acc[be][1]), pack_bf(acc[be][2], acc[be][3]));
    SPLIT();
    uint32_t F[66], qd[8][4];
    const uint32_t fa = tb + T_D + 32 + 4 * x;
#pragma unroll
    for (int i = 0; i < 32; i++) {
      const int s = 120 - (i >> 2) - 8 * (i & 3);
      uint32_t(&q)[4] = qd[i & 7];
      ldsm4(q, qa + 16 * s);
      const int m = 16 * (i & 3) + 2 * (i >> 2);
      F[m] = lds32(fa + 32 * m); F[m + 1] = lds32(fa + 32 * m + 32);
#pragma unroll
      for (int be = 15; be >= 12; be--) {
        const int de = 8 * be - s;
        float(&a)[4] = (be >= 14 && !(i & 1)) ? acc[be - 4] : acc[be];
        if (de >= 0 && be >= 14 && i == 2 * (15 - be)) mma0(a[0], a[1], a[2], a[3], q[0], q[1], q[2], q[3], F[2 * de + 1], F[2 * de]);
        else if (de >= 0) mma(a[0], a[1], a[2], a[3], q[0], q[1], q[2], q[3], F[2 * de + 1], F[2 * de]);
      }
    }
#pragma unroll
    for (int i = 0; i < 8; i++) acc[14 + (i >> 2)][i & 3] += acc[10 + (i >> 2)][i & 3];
    F[64] = lds32(fa + 32 * 64); F[65] = lds32(fa + 32 * 65);
    uint32_t qp = qa + 128 * 11, sta = st + 256 * 10;
    uint4* yd = ydst + 7 * 32;
#pragma unroll
    for (int i = 0; i < 6; i++) ldsm4(qd[i], qp - 16 * i);
    uint2 sv = lds64(sta + 256);
    float ci[4] = {bf_lo(sv.x), bf_hi(sv.x), bf_lo(sv.y), bf_hi(sv.y)};
    float T[5][4];
#pragma unroll
    for (int i = 0; i < 16; i++) T[i >> 2][i & 3] = acc[12 + (i >> 2)][i & 3];
    nb_sync(NB_YZ, 160);
    TS(46);
#pragma unroll 1
    for (int bp = 5; bp >= 0; bp--) {
      uint32_t held[2];
#pragma unroll
      for (int o = 1; o >= 0; o--) {
#pragma unroll
        for (int k = 4; k >= 1; k--) mmac(T[k], qd[0][0], qd[0][1], qd[0][2], qd[0][3], F[16 * k + 1], F[16 * k], T[k - 1]);
        mmac(T[0], qd[0][0], qd[0][1], qd[0][2], qd[0][3], F[1], F[0], ci);
        ldsm4(qd[6], qp - 16 * 6);
        ldsm4(qd[7], qp - 16 * 7);
        sv = lds64(sta);
#pragma unroll
        for (int i = 1; i < 8; i++) {
#pragma unroll
          for (int k = 3; k >= 0; k--)
            mma(T[k][0], T[k][1], T[k][2], T[k][3], qd[i][0], qd[i][1], qd[i][2], qd[i][3], F[16 * k + 2 * i + 1], F[16 * k + 2 * i]);
          if (i < 7) ldsm4(qd[i - 1], qp - 128 - 16 * (i - 1));
          if (i == 2) {
            const uint32_t w0 = pack_bf(T[4][0], T[4][1]), w1 = pack_bf(T[4][2], T[4][3]);
            if (o) { held[0] = w0; held[1] = w1; }
            else st_x(yd, nz(w0), w1, held[0], held[1]);
          }
          if (i == 4) {
            if (2 * bp + o <= 4) sv = make_uint2(0, 0);
            ci[0] = bf_lo(sv.x); ci[1] = bf_hi(sv.x); ci[2] = bf_lo(sv.y); ci[3] = bf_hi(sv.y);
          }
        }
        qp -= 128; sta -= 256;
      }
      yd -= 32;
      if (!(bp & 1)) nb_arrive(NB_Y + 1 + (bp >> 1), 160);
    }
#pragma unroll
    for (int B = 1; B >= 0; B--)
      st_x(ydst + B * 32, nz(pack_bf(T[2 * B][0], T[2 * B][1])), pack_bf(T[2 * B][2], T[2 * B][3]),
           pack_bf(T[2 * B + 1][0], T[2 * B + 1][1]), pack_bf(T[2 * B + 1][2], T[2 * B + 1][3]));
  }
}

__device__ __forceinline__ void dual_exp(const uint32_t* w, uint32_t* e) {
  const float L = 1.44268798828125f;
  uint32_t mx = bmax2(bmax2(w[0], w[1]), bmax2(w[2], w[3]));
  uint32_t mn = bmin2(bmin2(w[0], w[1]), bmin2(w[2], w[3]));
  mx = bmax2(mx, __shfl_xor_sync(0xffffffffu, mx, 1));
  mn = bmin2(mn, __shfl_xor_sync(0xffffffffu, mn, 1));
  mx = bmax2(mx, __shfl_xor_sync(0xffffffffu, mx, 2));
  mn = bmin2(mn, __shfl_xor_sync(0xffffffffu, mn, 2));
  const float mx0 = bf_lo(mx) * -L, mx1 = bf_hi(mx) * -L, mn0 = bf_lo(mn) * L, mn1 = bf_hi(mn) * L;
#pragma unroll
  for (int i = 0; i < 2; i++) {
    const float a0 = bf_lo(w[2 * i]), a1 = bf_hi(w[2 * i]), b0 = bf_lo(w[2 * i + 1]), b1 = bf_hi(w[2 * i + 1]);
    e[2 * i] = pack_bf(ex2(fmaf(a0, L, mx0)), ex2(fmaf(b0, L, mx0)));
    e[2 * i + 1] = pack_bf(ex2(fmaf(a1, L, mx1)), ex2(fmaf(b1, L, mx1)));
    e[4 + 2 * i] = pack_bf(ex2(fmaf(a0, -L, mn0)), ex2(fmaf(b0, -L, mn0)));
    e[5 + 2 * i] = pack_bf(ex2(fmaf(a1, -L, mn1)), ex2(fmaf(b1, -L, mn1)));
  }
}
__device__ __forceinline__ void normalise(uint32_t* e, const float (&s)[4]) {
  const uint32_t r = pack_bf(rcp(s[0]), rcp(s[2]));
  const __nv_bfloat162 rr = *(const __nv_bfloat162*)&r;
#pragma unroll
  for (int i = 0; i < 4; i++) {
    const __nv_bfloat162 v = __hmul2(*(const __nv_bfloat162*)&e[i], (i & 1) ? __high2bfloat162(rr) : __low2bfloat162(rr));
    e[i] = *(const uint32_t*)&v;
  }
}
__host__ __device__ constexpr uint64_t qdesc(uint32_t addr) { return mkdesc(addr, 128, 256, 0); }

__global__ void __launch_bounds__(NTHREADS, 1)
fused_kernel(const Params P, const __grid_constant__ CUtensorMap mx, const __grid_constant__ CUtensorMap mw,
             const __grid_constant__ CUtensorMap mo, const __grid_constant__ CUtensorMap mu,
             const __grid_constant__ CUtensorMap mout, const __grid_constant__ CUtensorMap mw4) {
  constexpr uint32_t sb = SB;
  const int tid = threadIdx.x, lane = tid & 31;
  const int warp = __shfl_sync(0xffffffffu, tid >> 5, 0);
  const int b = blockIdx.x, oct = b >> 3, i8 = b & 7;
  const int rt = (((oct & 4) ? ~oct : oct) & 3) * 2 + (i8 >> 2);
  const int hp = (oct >> 2) * 4 + (i8 & 3);

  const int wg = warp >> 2, w = warp & 3;
  const int d = b * 4 + ((tid >> 5) & 3);
  const KgenRaw raw = kgen_load(P, d, tid >> 7, lane);
  const unsigned short dsk = __ldg((const unsigned short*)P.Dskip + d);
  if (warp == 15) {
    asm volatile("prefetch.tensormap [%0];" ::"l"(&mu) : "memory");
    asm volatile("prefetch.tensormap [%0];" ::"l"(&mw) : "memory");
    asm volatile("prefetch.tensormap [%0];" ::"l"(&mx) : "memory");
    asm volatile("prefetch.tensormap [%0];" ::"l"(&mw4) : "memory");
  }
  if (warp == 12) {
    if (lane == 0) {
#pragma unroll
      for (int i = 0; i < 9; i++) mbar_init(BAR(i), 1);
      asm volatile("fence.mbarrier_init.release.cluster;" ::: "memory");
    }
    __syncwarp();
    if (lane < 9) mbar_expect(BAR(0) + 8 * lane, (lane == 5 || lane == 7) ? 40960 : ((lane == 0 || lane > 5) ? 16384 : 28672));
    __syncwarp();
    e_tma3d(sb + OFF_W, &mw, BAR(MB_FULL), hp * 32, 0, 0);
    e_tma2d(sb + OFF_X + 3 * 16384, &mx, BAR(MB_FULL), 0, rt * 256);
    nb_arrive(NB_PROD, 512);
  } else if (warp == 14) {
    e_prefetch(P.x + (size_t)(rt * 256 + hp * 8) * 512, 8192);
  } else if (warp == 13) {
    if (lane == 0) {
#pragma unroll
      for (int i = 9; i < 40; i++) mbar_init(BAR(i), i < MB_EMPTY ? 1 : 4);
      asm volatile("fence.mbarrier_init.release.cluster;" ::: "memory");
    }
    __syncwarp();
    if (lane < 14 && lane != 9) mbar_expect(BAR(MB_FULL + 8) + 8 * lane, lane == 8 ? 131072 : (lane == 10 ? 8192 : (lane == 13 ? 24576 : 16384)));
    nb_arrive(NB_PROD, 512);
  }
  const uint32_t tb = sb + OFF_T + w * T_CH;
  const uint32_t kp = wg == 2 ? sb + OFF_STG0 + 16384 + w * 1024 : ((tb + 127) & ~127u) + (wg == 3 ? 2 : wg) * 1536;
  const KgenAddr kad = kgen_addr(lane, kp);
  if ((warp >> 1) != 6) nb_sync(NB_PROD, 512);
  else nb_sync(NB_GATE + 1, 64);
  if (warp == 12) {
#pragma unroll 1
    for (int kb = 1; kb < 4; kb++) {
      if (kb == U_AT) e_tma4d(sb + OFF_STG0, &mu, BAR(MB_URAW), i8 * 64, oct * 2);
      e_tma3d(sb + OFF_W + kb * 12288, &mw, BAR(MB_FULL) + 8 * kb, hp * 32, kb * 64, 0);
      e_tma2d(sb + OFF_X + (kb < 2 ? kb + 3 : kb - 2) * 16384, &mx, BAR(MB_FULL) + 8 * kb, kb * 64, rt * 256);
    }
    e_tma4d(sb + OFF_W + 4 * 12288, &mw4, BAR(MB_FULL + 4), hp * 32, 4);
    e_tma2d(sb + OFF_X + 2 * 16384, &mx, BAR(MB_FULL + 4), 256, rt * 256);
    e_tma4d(sb + OFF_W + 6 * 12288, &mw4, BAR(MB_FULL + 6), hp * 32, 6);
    if (smem_u32(smem_raw) != SB) __trap();
    if (lane == 0) TS1(54);
  }
  float k[5][4], k2048, ksc;
  kgen_unit(raw, kad, blockIdx.y, k, k2048, ksc);
  TS(40 + wg);
  if ((fu(k[0][0]) & fu(k[1][0]) & fu(k[2][0]) & fu(k[3][0]) & fu(k[4][0])) == 0xffffffffu) sts32(kp, 0);
  if (wg) nb_arrive(0, 512);
  k2048 += __shfl_xor_sync(0xffffffffu, k2048, 16);
  k2048 += __shfl_xor_sync(0xffffffffu, k2048, 8);
  if (wg != 2) {
    uint32_t h[10];
#pragma unroll
    for (int j = 0; j < 10; j++) h[j] = hu(__floats2half2_rn(k[j >> 1][2 * (j & 1)], k[j >> 1][2 * (j & 1) + 1]));
    sts128(kp + lane * 16, h[0], h[1], h[2], h[3]);
    sts128(kp + 512 + lane * 16, h[4], h[5], h[6], h[7]);
    sts128(kp + 1024 + lane * 16, h[8], h[9], fu(k2048), fu(ksc));
  }
  if (wg == 0) { nb_arrive(NB_PREP, 512); nb_sync(0, 512); }
  else if (wg != 2) nb_arrive(NB_PREP, 512);
  else nb_sync(NB_PREP, 512);
  if (warp >= 12) {
    asm volatile("setmaxnreg.dec.sync.aligned.u32 32;");
    if (warp == 12) {
      if (X2_AT < 0) e_prefetch(P.x + (size_t)(rt * 256 + 128 + hp * 8) * 512, 8192);
      uint32_t slot = sb + OFF_X + 3 * 16384;
#pragma unroll 1
      for (int n = 0; n < 11; n++) {
        mbar_spin(BAR(MB_EMPTY) + 8 * n);
        const int m = n + 5;
        e_tma2d(slot, &mx, BAR(MB_FULL) + 8 * m, (m & 7) * 64, rt * 256 + (m >> 3) * 128);
        slot = slot == sb + OFF_X + 4 * 16384 ? sb + OFF_X : slot + 16384;
        if (n == X2_AT) e_prefetch(P.x + (size_t)(rt * 256 + 128 + hp * 8) * 512, 8192);
        if (n == 7) {
          e_prefetch(P.wo + (size_t)b * 2048, 4096);
          asm volatile("prefetch.tensormap [%0];" ::"l"(&mo) : "memory");
          asm volatile("prefetch.tensormap [%0];" ::"l"(&mout) : "memory");
        }
      }
#pragma unroll 1
      for (int i = 0; i < 8; i++) {
        mbar_wait(BAR(MB_EMPTY + 10) + 8 * ((0x54332222u >> (4 * i)) & 7));
        const int w0 = (0x54736210u >> (4 * i)) & 7;
        e_tma3d(sb + OFF_W + w0 * 16384, &mo, BAR(MB_WO), 0, w0 * 64, (hp & 3) * 2);
      }
    } else {
      if (warp == 15) {
        const uint4 v0 = __ldg((const uint4*)P.wphi + hp * 64 + lane), v1 = __ldg((const uint4*)P.wphi + hp * 64 + 32 + lane);
        sts128(sb + OFF_PHI + (lane & 1) * 256 + (lane >> 1) * 16, v0.x, v0.y, v0.z, v0.w);
        sts128(sb + OFF_PHI + 512 + (lane & 1) * 256 + (lane >> 1) * 16, v1.x, v1.y, v1.z, v1.w);
        const uint32_t one = (((lane >> 3) ^ (lane >> 4)) & 1) ? 0u : ((lane & 1) ? 0x3F800000u : 0x3F80u);
        const int q = (lane >> 1) & 3;
        sts128(sb + OFF_EYE + lane * 16, q == 0 ? one : 0u, q == 1 ? one : 0u, q == 2 ? one : 0u, q == 3 ? one : 0u);
        sts64(sb + OFF_ONE + lane * 8, 0x3F803F80u, 0x3F803F80u);
        asm volatile("fence.proxy.async.shared::cta;" ::: "memory");
        nb_arrive(NB_KREAD, 160);
      }
      uint32_t* cnt = (uint32_t*)(P.xs + X_CNT) + (warp == 13 ? i8 : (warp == 14 ? 8 + rt : 16 + oct)) * 32;
      const unsigned target = (ld_x32(cnt) & ~15u) + 16;
      if (warp != 14) {
        if (warp == 15) mbar_wait(BAR(MB_EMPTY + ZERO_STEP));
        uint4* pz = P.xs + (warp == 13 ? X_PART + (hp * 8 + rt) * 144 : X_Y + b * 1024) + lane;
#pragma unroll 1
        for (int i = (warp == 13 ? 144 : 1024) - lane; i > 0; i -= 32, pz += 32) st_x(pz, 0, 0, 0, 0);
      }
      if (warp == 15) __syncwarp();
      else nb_sync(warp == 13 ? NB_INIT : NB_ODONE, warp == 13 ? 160 : 288);
      if (lane == 0) asm volatile("red.release.gpu.global.add.u32 [%0], %1;" ::"l"(cnt), "r"(warp == 15 ? 2 : 1) : "memory");
      if (lane == 0) TS1(warp == 13 ? 50 : (warp == 14 ? 57 : 53));
      __syncwarp();
      if (warp == 14) nb_arrive(NB_GATE + 1, 160);
      asm volatile("fence.proxy.async.shared::cta;" ::: "memory");
      if (warp == 13) cnt += ((lane & 1 ? b >> 4 : i8 ^ (lane & 4)) - i8) * 32;
#pragma unroll 1
      for (int i = 0; i < SPIN_MAX; i++) {
        unsigned v;
        asm volatile("ld.acquire.gpu.global.u32 %0, [%1];" : "=r"(v) : "l"(cnt) : "memory");
        if (__all_sync(0xffffffffu, (int)(v - target) >= 0)) break;
      }
      if (lane == 0) TS1(warp == 13 ? 51 : (warp == 14 ? 58 : 55));
      if (warp == 15) { nb_arrive(NB_YZ, 160); return; }
      asm volatile("fence.proxy.async.global;" ::: "memory");
      if (warp == 13) {
        mbar_wait(BAR(MB_EMPTY + 11));
        e_expect(BAR(MB_UFULL), 4 * U_CH);
        e_bulk(sb + OFF_U, P.xs + X_UT + b * (U_CH / 4), 4 * U_CH, BAR(MB_UFULL));
      } else {
        const uint4* src = P.xs + X_O + (rt * 4 + (hp >> 2)) * 4096;
        e_bulk(sb + OFF_X + 32768 + 57344, src + 3584, 8192, BAR(MB_O));
        e_bulk(sb + OFF_X + 32768, src, 16384, BAR(MB_O + 1));
        e_bulk(sb + OFF_X + 49152, src + 1024, 16384, BAR(MB_O + 2));
        e_bulk(sb + OFF_STG0, src + 3200, 6144, BAR(MB_O + 3));
        nb_sync(NB_BDONE, 288);
        asm volatile("fence.proxy.async.shared::cta;" ::: "memory");
        e_bulk(sb + OFF_U, src + 2048, 18432, BAR(MB_O + 3));
      }
    }
    return;
  }

  const int t = tid & 127;
  const int g = lane >> 2, c = lane & 3;
  if (wg == 1) {
    mbar_wait(BAR(MB_URAW));
    TS(48);
    uint4* dst = P.xs + X_UT + (i8 * 64 + g) * (U_CH / 16) + (w & 1) * (U_ODD / 16) + U_PAD / 16 + oct * 8 + (w >> 1) * 4 + c;
    const int ln = ((lane >> 1) & 3) + 4 * (lane & 1);
    uint32_t r[8][4];
#pragma unroll
    for (int i = 0; i < 8; i++) ldsm4t(r[i], sb + OFF_STG0 + w * 4096 + ((lane >> 3) * 8 + ln) * 128 + ((i ^ ln) << 4));
#pragma unroll
    for (int i = 0; i < 8; i++) dst[i * (U_CH / 2)] = make_uint4(r[i][0], r[i][1], r[i][2], r[i][3]);
    nb_arrive(NB_INIT, 160);
    if (lane == 0) mbar_arrive(BAR(MB_AUX));
  }
  {
    if (wg == 2) {
      asm volatile("setmaxnreg.inc.sync.aligned.u32 160;");
#pragma unroll
      for (int j = 0; j < 5; j++) { k[j][0] *= ksc; k[j][1] *= ksc; k[j][2] *= ksc; k[j][3] *= ksc; }
#pragma unroll 1
      for (int q = 0; q < 3; q++) {
        const uint32_t src = ((tb + 127) & ~127u) + q * 1536 + lane * 16;
        const uint4 v0 = lds128(src), v1 = lds128(src + 512), v2 = lds128(src + 1024);
        const uint32_t h[10] = {v0.x, v0.y, v0.z, v0.w, v1.x, v1.y, v1.z, v1.w, v2.x, v2.y};
#pragma unroll
        for (int j = 0; j < 10; j++) {
          const float2 f = __half22float2(*(const __half2*)&h[j]);
          k[j >> 1][2 * (j & 1)] = fmaf(f.x, uf(v2.w), k[j >> 1][2 * (j & 1)]);
          k[j >> 1][2 * (j & 1) + 1] = fmaf(f.y, uf(v2.w), k[j >> 1][2 * (j & 1) + 1]);
        }
        k2048 += uf(v2.z);
      }
#pragma unroll
      for (int o2 = 4; o2; o2 >>= 1) k2048 += __shfl_xor_sync(0xffffffffu, k2048, o2);
      if (lane == 0) k[0][0] += bf_lo(dsk);
      __syncwarp();
      TS(34);
      build_tables(tb, lane, k, k2048);
      TS(35);
      uint4* const g_y = P.xs + X_Y;
      conv_channel(sb + OFF_U + w * U_CH, tb, lane, g_y + (size_t)d * 256 + lane);
      nb_arrive(NB_BDONE, 288);
      nb_arrive(NB_Y, 160);
      TS(37);
      if (w == 0) TSDUMP(32);
      return;
    }
    if (wg == 1) {
      mbar_wait(BAR(MB_EMPTY + 4));
      mbar_spin(BAR(MB_EMPTY + 6));
    }
    TS(wg * 16 + 1);
  }

  float acc[2][48];
  {
    uint32_t fb = BAR(MB_FULL) + 64 * wg;
    uint32_t da = (uint32_t)mkdesc(sb + OFF_X, 16, 0, 0) + (wg ? 1024 : 3072), db = (uint32_t)mkdesc(sb + OFF_W, 4096, 0, 0);
    constexpr uint64_t ha = mkdesc(0, 0, 1024, 1), hb = mkdesc(0, 0, 512, 2);
    mbar_spin(fb);
    TS(wg * 16 + 2);
#pragma unroll 1
    for (int kb = 0; kb < 8; kb++) {
      WG_FENCE();
#pragma unroll
      for (int k = 0; k < 4; k++) {
        wgmma_ss_n96(acc[0], ha | (da + 2 * k), hb | (db + 64 * k), k ? 1 : kb);
        wgmma_ss_n96(acc[1], ha | (da + 2 * k + 512), hb | (db + 64 * k), k ? 1 : kb);
      }
      WG_COMMIT();
      if (kb < 7) mbar_spin(fb + 8);
      WG_WAIT(1);
      if (kb > 0) e_arrive(fb + 8 * (MB_EMPTY - MB_FULL - 1));
      fb += 8; db += 768;
      da = da == (uint32_t)mkdesc(sb + OFF_X + 65536, 16, 0, 0) ? da - 4096 : da + 1024;
    }
    if (wg == 0) nb_sync(NB_KREAD, 160);
    asm volatile("setmaxnreg.inc.sync.aligned.u32 160;");
    WG_WAIT(0);
    e_arrive(fb + 8 * (MB_EMPTY - MB_FULL - 1));
    SPLIT();
  }
  TS(wg * 16 + 3);

  constexpr uint32_t stg0 = sb + OFF_STG0, stg1 = sb + OFF_X + 32768;
  uint4* const g_part = P.xs + X_PART;
  uint4* const g_o = P.xs + X_O;
  constexpr uint32_t kvs = stg0;
  auto pack8 = [](const float* a) { return make_uint4(pack_bf(a[0], a[1]), pack_bf(a[2], a[3]), pack_bf(a[4], a[5]), pack_bf(a[6], a[7])); };
  auto feat = [&](const uint4 (&af)[4], float (&p)[4][8]) {
    WG_FENCE();
#pragma unroll
    for (int u = 0; u < 4; u++) wgmma_rs_n16(p[u], af[u], qdesc(sb + OFF_PHI + (u & 1) * 512), 0);
    WG_COMMIT();
  };
  auto packp = [](const float (&p)[4][8], uint32_t (&pw)[16]) {
#pragma unroll
    for (int i = 0; i < 16; i++) pw[i] = pack_bf(p[i >> 2][(i & 1) + 2 * (i & 2)], p[i >> 2][(i & 1) + 2 * (i & 2) + 2]);
  };
  auto contract = [&](float (&kc)[20], uint32_t stg, int acc_in) {
    WG_FENCE();
#pragma unroll
    for (int s = 0; s < 8; s++) wgmma_ss_n40(kc, qdesc(stg + s * SLAB), qdesc(stg + s * SLAB + 2048), s ? 1 : acc_in);
    WG_COMMIT();
    WG_WAIT(0);
  };
  uint32_t eq[32];
  {
    uint4 af[4], aq[4], vp[4];
    float p[4][8];
#pragma unroll
    for (int u = 0; u < 4; u++) af[u] = pack8(acc[u >> 1] + 16 + 8 * (u & 1));
    feat(af, p);
#pragma unroll
    for (int u = 0; u < 4; u++) { aq[u] = pack8(acc[u >> 1] + 8 * (u & 1)); vp[u] = pack8(acc[u >> 1] + 32 + 8 * (u & 1)); }
    WG_WAIT(0);
    uint32_t pw[16], ek[32];
    packp(p, pw);
#pragma unroll
    for (int u = 0; u < 4; u++) dual_exp(pw + 4 * u, ek + 8 * u);
    TS(wg * 16 + 12);
    mbar_spin(wg ? BAR(MB_EMPTY + 15) : BAR(MB_AUX));
    float rs[8][4];
    WG_FENCE();
#pragma unroll
    for (int i = 0; i < 8; i++) wgmma_rs_n8(rs[i], make_uint4(ek[4 * i], ek[4 * i + 1], ek[4 * i + 2], ek[4 * i + 3]), qdesc(sb + OFF_ONE), 0);
    WG_COMMIT();
    feat(aq, p);
    const uint32_t sl = (wg ? stg1 : stg0) + w * SLAB + lane * 16;
#pragma unroll
    for (int i = 0; i < 4; i++) stsm4(sl + (i >> 1) * 4 * SLAB + 2048 + (i & 1) * 512, vp[i].x, vp[i].y, vp[i].z, vp[i].w);
    sts128(sl + (lane >> 4) * (4 * SLAB - 256) + 3072, 0x3F803F80u, 0x3F803F80u, 0x3F803F80u, 0x3F803F80u);
    WG_WAIT(1);
#pragma unroll
    for (int i = 0; i < 8; i++) {
      normalise(ek + 4 * i, rs[i]);
      stsm4(sl + (i >> 2) * 4 * SLAB + (i & 3) * 512, ek[4 * i], ek[4 * i + 1], ek[4 * i + 2], ek[4 * i + 3]);
    }
    asm volatile("fence.proxy.async.shared::cta;" ::: "memory");
    TS(wg * 16 + 13);
    if (wg) {
      nb_arrive(NB_ST0, 256);
    } else {
      float kc[20];
      uint4* pp = g_part + (size_t)(hp * 8 + rt) * 144 + t;
      uint32_t* pz = (uint32_t*)(pp - t + 128) + w * 16 + c * 8 + g;
      asm volatile("" : "+l"(pp), "+l"(pz));
      nb_sync(NB_WG0, 128);
      contract(kc, stg0, 0);
      mbar_wait(BAR(MB_UFULL));
      TS(15);
      nb_sync(NB_ST0, 256);
      contract(kc, stg1, 1);
      TS(6);
      float kv[8];
#pragma unroll
      for (int i = 0; i < 8; i++) kv[i] = w & 2 ? kc[8 + i] : kc[i];
      st_x(pp, nz(pack_bf(kv[0], kv[1])), pack_bf(kv[2], kv[3]), pack_bf(kv[4], kv[5]), pack_bf(kv[6], kv[7]));
      if (c < 2) st_x32(pz, nz(fu(c ? kc[18] : kc[16])));
      TS(5);
    }
    SPLIT();
    WG_WAIT(0);
    packp(p, pw);
#pragma unroll
    for (int u = 0; u < 4; u++) dual_exp(pw + 4 * u, eq + 8 * u);
    SPLIT();
  }
  TS(wg * 16 + 4);
  if (wg == 1) {
    mbar_wait(BAR(MB_UFULL));
    const uint4* ps = g_part + (size_t)hp * 8 * 144 + t;
    const uint32_t* zs = (const uint32_t*)(g_part + (size_t)(hp * 8 + (lane >> 4) * 4) * 144 + 128) + w * 16 + (lane & 15);
    uint4 v[8];
    uint32_t zv[4];
#pragma unroll 1
    for (int it = 0; it < SPIN_MAX; it++) {
#pragma unroll
      for (int i = 0; i < 8; i++) v[i] = ld_x(ps + i * 144);
#pragma unroll
      for (int i = 0; i < 4; i++) zv[i] = ld_x32(zs + i * 576);
      uint32_t m = min(min(zv[0], zv[1]), min(zv[2], zv[3]));
#pragma unroll
      for (int i = 0; i < 8; i++) m = min(m, v[i].x);
      if (__all_sync(0xffffffffu, m != 0)) break;
    }
    float s[8];
    WG_FENCE();
#pragma unroll
    for (int r = 0; r < 8; r++) wgmma_rs_n16(s, v[r], qdesc(sb + OFF_EYE), r);
    WG_COMMIT();
    float zsum = (uf(zv[0]) + uf(zv[1])) + (uf(zv[2]) + uf(zv[3]));
    zsum += __shfl_xor_sync(0xffffffffu, zsum, 16);
    const uint32_t z1 = pack_bf(zsum, 1.f);
    if (lane < 16) sts128(kvs + w * 768 + 512 + lane * 16, z1, z1, z1, z1);
    WG_WAIT(0);
    stsm4(kvs + w * 768 + lane * 16, pack_bf(s[0], s[1]), pack_bf(s[2], s[3]), pack_bf(s[4], s[5]), pack_bf(s[6], s[7]));
    asm volatile("fence.proxy.async.shared::cta;" ::: "memory");
    TS(22);
  }
  nb_sync(NB_KV, 256);
  {
    float n[8][12];
    WG_FENCE();
#pragma unroll
    for (int i = 0; i < 8; i++) wgmma_rs_n24(n[i], make_uint4(eq[4 * i], eq[4 * i + 1], eq[4 * i + 2], eq[4 * i + 3]), qdesc(kvs + (i & 3) * 768), 0);
    WG_COMMIT();
    uint32_t* od = (uint32_t*)(g_o + (size_t)((rt * 4 + wg * 2) * 32 + hp * 2) * 128) + w * 64 + lane;
    WG_WAIT(0);
#pragma unroll
    for (int u = 0; u < 4; u++) {
      float(&np)[12] = n[2 * u];
      const float(&nm)[12] = n[2 * u + 1];
      const float q0 = np[9] * rcp(nm[9]), q1 = np[11] * rcp(nm[11]);
      const float r0 = rcp(fmaf(nm[8], q0, fmaf(np[9], 1e-6f, np[8]))), r1 = rcp(fmaf(nm[10], q1, fmaf(np[11], 1e-6f, np[10])));
#pragma unroll
      for (int i = 0; i < 8; i++) np[i] = fmaf(nm[i], (i & 2) ? q1 : q0, np[i]);
      uint32_t* o = od + (u >> 1) * 16384 + (u & 1) * 512;
      o[0] = pack_bf(np[0] * r0, np[1] * r0);
      o[32] = pack_bf(np[2] * r1, np[3] * r1);
      o[256] = pack_bf(np[4] * r0, np[5] * r0);
      o[288] = pack_bf(np[6] * r1, np[7] * r1);
      if (u == 1) SPLIT();
    }
  }
  TS(wg * 16 + 7);
  nb_arrive(NB_ODONE, 288);
  if (wg) {
    const uint4* src = P.xs + X_Y + (oct * 32 + c * 8) * 256 + (2 * w + (g >> 2)) * 32 + i8 * 4 + (g & 3);
    __nv_bfloat16* dst = P.out + (size_t)((2 * w + (g >> 2)) * 256 + i8 * 16 + (g & 3) * 2) * 1024 + 512 + oct * 32 + c * 8;
    nb_sync(NB_GATE + 1, 160);
    nb_sync(NB_Y + w, 160);
    uint4 v[8];
#pragma unroll 1
    for (int it = 0; it < SPIN_MAX; it++) {
      uint32_t m = 0xffffffffu;
#pragma unroll
      for (int i = 0; i < 8; i++) v[i] = ld_x(src + i * 256);
#pragma unroll
      for (int i = 0; i < 8; i++) m = min(m, v[i].x);
      if (__all_sync(0xffffffffu, m != 0)) break;
    }
#pragma unroll
    for (int i = 0; i < 8; i++) *(uint4*)(dst + (size_t)((i >> 2) * 128 + ((i >> 1) & 1) * 8 + (i & 1)) * 1024) = tr_row(v, i);
    TS(31);
    GT(63);
    if (w == 0) TSDUMP(16);
    return;
  }
  mbar_wait(BAR(MB_WO));
  nb_sync(NB_BDONE, 288);
  TS(8);
  mbar_spin(BAR(MB_O));
  TS(9);
  constexpr uint64_t ha = mkdesc(0, 0, 128, 0), hb = mkdesc(0, 0, 1024, 1);
  constexpr uint32_t da0 = (uint32_t)mkdesc(stg1, 1024, 0, 0), db0 = (uint32_t)mkdesc(sb + OFF_W, 8192, 0, 0);
  const uint32_t ot = ((sb + OFF_T + 1023) & ~1023u) + w * 4096;
  auto store_half = [&](const float* oc, int hf) {
#pragma unroll
    for (int i = 0; i < 8; i += 2)
      stsm4(ot + hf * 2048 + (lane & 15) * 128 + (((i + (lane >> 4)) ^ lane) & 7) * 16, pack_bf(oc[4 * i], oc[4 * i + 1]),
            pack_bf(oc[4 * i + 2], oc[4 * i + 3]), pack_bf(oc[4 * i + 4], oc[4 * i + 5]), pack_bf(oc[4 * i + 6], oc[4 * i + 7]));
    asm volatile("fence.proxy.async.shared::cta;" ::: "memory");
    __syncwarp();
    e_store2d(&mout, ot + hf * 2048, (hp & 3) * 128 + hf * 64, (rt * 4 + (hp >> 2)) * 64 + w * 16);
  };
  float oc[64];
#pragma unroll 1
  for (int j = 0; j < 8; j++) {
    const int kb = (j + 7) & 7;
    if ((j & 1) && j < 6) mbar_spin(BAR(MB_O + 1) + 4 * (j - 1));
    WG_FENCE();
#pragma unroll
    for (int k = 0; k < 4; k++) wgmma_ss_n128(oc, ha | (da0 + 512 * kb + 128 * k), hb | (db0 + 1024 * kb + 128 * k), k ? 1 : j);
    WG_COMMIT();
  }
  WG_WAIT(0);
  TS(10);
  store_half(oc, 0);
  store_half(oc + 32, 1);
  asm volatile(ELECT "cp.async.bulk.commit_group;\n@p cp.async.bulk.wait_group.read 0;\n}\n" ::: "memory");
  TS(wg * 16 + 11);
  GT(61 + wg);
  if (w == 0) TSDUMP(0);
  if (w == 1) TSDUMP(48);
}

typedef CUresult (*EncodeFn)(CUtensorMap*, CUtensorMapDataType, cuuint32_t, void*, const cuuint64_t*, const cuuint64_t*,
                             const cuuint32_t*, const cuuint32_t*, CUtensorMapInterleave, CUtensorMapSwizzle,
                             CUtensorMapL2promotion, CUtensorMapFloatOOBfill);

}

extern "C" void kernel_launch(void* const* d_in, const int* in_sizes, int n_in, void* d_out, int out_size) {
  (void)in_sizes; (void)n_in; (void)out_size;
  void* fn = nullptr;
  cudaDriverEntryPointQueryResult qr;
  cudaGetDriverEntryPoint("cuTensorMapEncodeTiled", &fn, cudaEnableDefault, &qr);
  EncodeFn enc = (EncodeFn)fn;
  CUtensorMap mx, mw, mo, mu, mout, mw4;
  const cuuint32_t es[5] = {1, 1, 1, 1, 1};
  {
    cuuint64_t dims[2] = {512, 2048}, st[1] = {1024};
    cuuint32_t box[2] = {64, 128};
    enc(&mx, CU_TENSOR_MAP_DATA_TYPE_BFLOAT16, 2, d_in[0], dims, st, box, es, CU_TENSOR_MAP_INTERLEAVE_NONE,
        CU_TENSOR_MAP_SWIZZLE_128B, CU_TENSOR_MAP_L2_PROMOTION_L2_128B, CU_TENSOR_MAP_FLOAT_OOB_FILL_NONE);
  }
  {
    cuuint64_t dims[3] = {512, 512, 3}, st[2] = {3072, 1024};
    cuuint32_t box[3] = {32, 64, 3};
    enc(&mw, CU_TENSOR_MAP_DATA_TYPE_BFLOAT16, 3, d_in[1], dims, st, box, es, CU_TENSOR_MAP_INTERLEAVE_NONE,
        CU_TENSOR_MAP_SWIZZLE_64B, CU_TENSOR_MAP_L2_PROMOTION_L2_128B, CU_TENSOR_MAP_FLOAT_OOB_FILL_NONE);
  }
  {
    cuuint64_t dims[3] = {64, 512, 8}, st[2] = {1024, 128};
    cuuint32_t box[3] = {64, 64, 2};
    enc(&mo, CU_TENSOR_MAP_DATA_TYPE_BFLOAT16, 3, d_in[3], dims, st, box, es, CU_TENSOR_MAP_INTERLEAVE_NONE,
        CU_TENSOR_MAP_SWIZZLE_128B, CU_TENSOR_MAP_L2_PROMOTION_L2_128B, CU_TENSOR_MAP_FLOAT_OOB_FILL_NONE);
  }
  {
    cuuint64_t dims[4] = {512, 4, 16, 32}, st[3] = {16384, 1024, 65536};
    cuuint32_t box[4] = {64, 4, 16, 2};
    enc(&mu, CU_TENSOR_MAP_DATA_TYPE_BFLOAT16, 4, d_in[4], dims, st, box, es, CU_TENSOR_MAP_INTERLEAVE_NONE,
        CU_TENSOR_MAP_SWIZZLE_128B, CU_TENSOR_MAP_L2_PROMOTION_L2_128B, CU_TENSOR_MAP_FLOAT_OOB_FILL_NONE);
  }
  {
    cuuint64_t dims[2] = {1024, 2048}, st[1] = {2048};
    cuuint32_t box[2] = {64, 16};
    enc(&mout, CU_TENSOR_MAP_DATA_TYPE_BFLOAT16, 2, d_out, dims, st, box, es, CU_TENSOR_MAP_INTERLEAVE_NONE,
        CU_TENSOR_MAP_SWIZZLE_128B, CU_TENSOR_MAP_L2_PROMOTION_NONE, CU_TENSOR_MAP_FLOAT_OOB_FILL_NONE);
  }
  {
    cuuint64_t dims[4] = {512, 64, 3, 8}, st[3] = {3072, 1024, 64 * 3072};
    cuuint32_t box[4] = {32, 64, 3, 2};
    enc(&mw4, CU_TENSOR_MAP_DATA_TYPE_BFLOAT16, 4, d_in[1], dims, st, box, es, CU_TENSOR_MAP_INTERLEAVE_NONE,
        CU_TENSOR_MAP_SWIZZLE_64B, CU_TENSOR_MAP_L2_PROMOTION_L2_128B, CU_TENSOR_MAP_FLOAT_OOB_FILL_NONE);
  }
  Params P;
  P.x = (const __nv_bfloat16*)d_in[0];
  P.wphi = (const __nv_bfloat16*)d_in[2];
  P.wo = (const __nv_bfloat16*)d_in[3];
  P.logA = (const __nv_bfloat16*)d_in[5];
  P.Aim = (const __nv_bfloat16*)d_in[6];
  P.Cre = (const __nv_bfloat16*)d_in[7];
  P.Cim = (const __nv_bfloat16*)d_in[8];
  P.logdt = (const __nv_bfloat16*)d_in[9];
  P.Dskip = (const __nv_bfloat16*)d_in[10];
  P.out = (__nv_bfloat16*)d_out;
  cudaGetSymbolAddress((void**)&P.xs, g_x);
  P.ts = nullptr;
  cudaFuncSetAttribute(fused_kernel, cudaFuncAttributeMaxDynamicSharedMemorySize, SMEM_BYTES);
  fused_kernel<<<NCTA, NTHREADS, SMEM_BYTES>>>(P, mx, mw, mo, mu, mout, mw4);
}
```

```cpp
#include <cuda_runtime.h>
#include <cuda_bf16.h>
#include <cuda_fp16.h>
#include <cuda.h>
#include <stdint.h>

#define DBG_TS 0

namespace {

constexpr int NTHREADS = 512;
constexpr int NCTA = 128;
constexpr int OFF_W = 0;
constexpr int OFF_X = 98304;
constexpr int OFF_U = OFF_X + 65536;
constexpr int U_CH = 4416, U_ODD = 2240, U_PAD = 128;
constexpr int OFF_STG0 = OFF_U + 18432;
constexpr int SLAB = 3328;
constexpr int OFF_T = OFF_STG0 + 8 * SLAB;
constexpr int T_CH = 5216;
constexpr int T_D = 0;
constexpr int T_5 = 2144;
constexpr int T_3 = T_5 + 384;
constexpr int T_7 = T_5 + 1024;
constexpr int T_9 = T_7 + 320;
constexpr int T_KC = T_9 + 320;
constexpr int T_ST = T_5 - 1024;
constexpr int OFF_PHI = OFF_T + 4 * T_CH;
constexpr int OFF_EYE = OFF_PHI + 1024, OFF_ONE = OFF_EYE + 512;
constexpr int OFF_BAR = OFF_ONE + 256;
constexpr int SMEM_BYTES = OFF_BAR + 512 + 256 * DBG_TS;
constexpr uint32_t SB = 1024;
static_assert(T_KC + 2 * 656 <= T_CH, "table size");
static_assert(SMEM_BYTES <= 232448, "smem");
constexpr int MB_URAW = 0, MB_FULL = 1  , MB_WO = 17, MB_UFULL = 18, MB_O = 19  ,
              MB_EMPTY = 23  , MB_AUX = 39;
__host__ __device__ constexpr uint32_t BAR(int i) { return SB + OFF_BAR + 8 * i; }
constexpr int NB_WG0 = 1, NB_ODONE = 2, NB_ST0 = 3  , NB_KV = 5, NB_YZ = 6, NB_INIT = 7, NB_PREP = 8, NB_PROD = 9, NB_KREAD = 10, NB_BDONE = 11, NB_GATE = 12,
              NB_Y = 7  ;
#define X2_AT -1
#define GATE_B 1
#define POLL 0
#define HM_SUM 1
#define HM_O 1
#define U_AT 2
#define ZERO_STEP 12
constexpr int SPIN_MAX = 1 << 16;

constexpr int X_CNT = 0;
constexpr int X_PART = 256;
constexpr int X_O = X_PART + 16 * 8 * 144;
constexpr int X_Y = X_O + 32 * 32 * 128;
constexpr int X_UT = X_Y + 512 * 8 * 32;
constexpr int X_SIZE = X_UT + 512 * (U_CH / 16);
__device__ __align__(128) uint4 g_x[X_SIZE];
extern __shared__ uint8_t smem_raw[];
#define TS(i) do {} while (0)
#define TS1(i) do {} while (0)
#define GT(i) do {} while (0)
#define TSDUMP(base) do {} while (0)

__device__ __forceinline__ uint32_t smem_u32(const void* p) { return (uint32_t)__cvta_generic_to_shared(p); }
__device__ __forceinline__ void mbar_arrive(uint32_t b) {
  asm volatile("mbarrier.arrive.shared::cta.b64 _, [%0];" ::"r"(b) : "memory");
}
__device__ __forceinline__ void mbar_wait(uint32_t b) {
  uint32_t done = 0;
#pragma unroll 1
  for (int i = 0; i < SPIN_MAX && !done; i++) {
    asm volatile("{\n.reg .pred p;\nmbarrier.try_wait.parity.shared::cta.b64 p, [%1], 0, 4000;\nselp.u32 %0, 1, 0, p;\n}\n"
                 : "=r"(done) : "r"(b) : "memory");
  }
}
__device__ __forceinline__ void mbar_spin(uint32_t b) {
  uint32_t done = 0;
#pragma unroll 1
  for (int i = 0; i < (SPIN_MAX << 4) && !done; i++) {
    asm volatile("{\n.reg .pred p;\nmbarrier.try_wait.parity.shared::cta.b64 p, [%1], 0;\nselp.u32 %0, 1, 0, p;\n}\n"
                 : "=r"(done) : "r"(b) : "memory");
  }
}
__device__ __forceinline__ void mbar_init(uint32_t b, int n) {
  asm volatile("mbarrier.init.shared::cta.b64 [%0], %1;" ::"r"(b), "r"(n) : "memory");
}
__device__ __forceinline__ void mbar_expect(uint32_t b, int bytes) {
  asm volatile("mbarrier.arrive.expect_tx.shared::cta.b64 _, [%0], %1;" ::"r"(b), "r"(bytes) : "memory");
}
__device__ __forceinline__ void nb_sync(int id, int n) { asm volatile("bar.sync %0, %1;" ::"r"(id), "r"(n) : "memory"); }
__device__ __forceinline__ void nb_arrive(int id, int n) { asm volatile("bar.arrive %0, %1;" ::"r"(id), "r"(n) : "memory"); }
#define ELECT "{\n.reg .pred p;\nelect.sync _|p, 0xffffffff;\n@p "
__device__ __forceinline__ void e_arrive(uint32_t b) {
  asm volatile(ELECT "mbarrier.arrive.shared::cta.b64 _, [%0];\n}\n" ::"r"(b) : "memory");
}
__device__ __forceinline__ void e_expect(uint32_t b, int bytes) {
  asm volatile(ELECT "mbarrier.arrive.expect_tx.shared::cta.b64 _, [%0], %1;\n}\n" ::"r"(b), "r"(bytes) : "memory");
}
__device__ __forceinline__ void e_tma2d(uint32_t dst, const CUtensorMap* m, uint32_t bar, int c0, int c1) {
  asm volatile(ELECT "cp.async.bulk.tensor.2d.shared::cluster.global.mbarrier::complete_tx::bytes [%0], [%1, {%3,%4}], [%2];\n}\n"
               ::"r"(dst), "l"(m), "r"(bar), "r"(c0), "r"(c1) : "memory");
}
__device__ __forceinline__ void e_tma3d(uint32_t dst, const CUtensorMap* m, uint32_t bar, int c0, int c1, int c2) {
  asm volatile(ELECT "cp.async.bulk.tensor.3d.shared::cluster.global.mbarrier::complete_tx::bytes [%0], [%1, {%3,%4,%5}], [%2];\n}\n"
               ::"r"(dst), "l"(m), "r"(bar), "r"(c0), "r"(c1), "r"(c2) : "memory");
}
__device__ __forceinline__ void e_tma4d(uint32_t dst, const CUtensorMap* m, uint32_t bar, int c0, int c3) {
  asm volatile(ELECT "cp.async.bulk.tensor.4d.shared::cluster.global.mbarrier::complete_tx::bytes [%0], [%1, {%3,%5,%5,%4}], [%2];\n}\n"
               ::"r"(dst), "l"(m), "r"(bar), "r"(c0), "r"(c3), "r"(0) : "memory");
}
__device__ __forceinline__ void e_bulk(uint32_t dst, const void* src, int bytes, uint32_t bar) {
  asm volatile(ELECT "cp.async.bulk.shared::cluster.global.mbarrier::complete_tx::bytes [%0], [%1], %2, [%3];\n}\n"
               ::"r"(dst), "l"(src), "r"(bytes), "r"(bar) : "memory");
}
__device__ __forceinline__ void e_prefetch(const void* p, int bytes) {
  asm volatile(ELECT "cp.async.bulk.prefetch.L2.global [%0], %1;\n}\n" ::"l"(p), "r"(bytes) : "memory");
}
__device__ __forceinline__ void e_store2d(const CUtensorMap* m, uint32_t src, int c0, int c1) {
  asm volatile(ELECT "cp.async.bulk.tensor.2d.global.shared::cta.bulk_group [%0, {%2,%3}], [%1];\n}\n"
               ::"l"(m), "r"(src), "r"(c0), "r"(c1) : "memory");
}
__host__ __device__ constexpr uint64_t mkdesc(uint32_t addr, uint32_t lbo, uint32_t sbo, int swz) {
  return (uint64_t)((addr & 0x3FFFF) >> 4) | ((uint64_t)(lbo >> 4) << 16) | ((uint64_t)(sbo >> 4) << 32) |
         ((uint64_t)swz << 62);
}
#define SPLIT() asm volatile("{\n.reg .pred p;\nsetp.eq.u32 p, %0, %1;\n@p exit;\n}\n" ::"r"(blockIdx.y), "n"(__LINE__) : "memory")
#define WG_FENCE() asm volatile("wgmma.fence.sync.aligned;" ::: "memory")
#define WG_COMMIT() asm volatile("wgmma.commit_group.sync.aligned;" ::: "memory")
#define WG_WAIT(n) asm volatile("wgmma.wait_group.sync.aligned " #n ";" ::: "memory")

__device__ __forceinline__ void mma(float& d0, float& d1, float& d2, float& d3, uint32_t a0, uint32_t a1, uint32_t a2,
                                    uint32_t a3, uint32_t b0, uint32_t b1) {
  asm volatile("mma.sync.aligned.m16n8k16.row.col.f32.bf16.bf16.f32 {%0,%1,%2,%3},{%4,%5,%6,%7},{%8,%9},{%0,%1,%2,%3};"
               : "+f"(d0), "+f"(d1), "+f"(d2), "+f"(d3)
               : "r"(a0), "r"(a1), "r"(a2), "r"(a3), "r"(b0), "r"(b1));
}
__device__ __forceinline__ void mmac(float (&d)[4], uint32_t a0, uint32_t a1, uint32_t a2, uint32_t a3, uint32_t b0,
                                     uint32_t b1, const float (&c)[4]) {
  asm volatile("mma.sync.aligned.m16n8k16.row.col.f32.bf16.bf16.f32 {%0,%1,%2,%3},{%4,%5,%6,%7},{%8,%9},{%10,%11,%12,%13};"
               : "=f"(d[0]), "=f"(d[1]), "=f"(d[2]), "=f"(d[3])
               : "r"(a0), "r"(a1), "r"(a2), "r"(a3), "r"(b0), "r"(b1), "f"(c[0]), "f"(c[1]), "f"(c[2]), "f"(c[3]));
}
__device__ __forceinline__ void mma_p(int p, float (&d)[4], uint32_t a0, uint32_t a1, uint32_t a2, uint32_t a3, uint32_t b0, uint32_t b1) {
  asm volatile("{\n.reg .pred q;\nsetp.ne.b32 q, %10, 0;\n"
               "@q mma.sync.aligned.m16n8k16.row.col.f32.bf16.bf16.f32 {%0,%1,%2,%3},{%4,%5,%6,%7},{%8,%9},{%0,%1,%2,%3};\n}\n"
               : "+f"(d[0]), "+f"(d[1]), "+f"(d[2]), "+f"(d[3])
               : "r"(a0), "r"(a1), "r"(a2), "r"(a3), "r"(b0), "r"(b1), "r"(p));
}
__device__ __forceinline__ void mmac_p(int p, float (&d)[4], uint32_t a0, uint32_t a1, uint32_t a2, uint32_t a3, uint32_t b0,
                                       uint32_t b1, const float (&c)[4]) {
  asm volatile("{\n.reg .pred q;\nsetp.ne.b32 q, %14, 0;\n"
               "@q mma.sync.aligned.m16n8k16.row.col.f32.bf16.bf16.f32 {%0,%1,%2,%3},{%4,%5,%6,%7},{%8,%9},{%10,%11,%12,%13};\n}\n"
               : "+f"(d[0]), "+f"(d[1]), "+f"(d[2]), "+f"(d[3])
               : "r"(a0), "r"(a1), "r"(a2), "r"(a3), "r"(b0), "r"(b1), "f"(c[0]), "f"(c[1]), "f"(c[2]), "f"(c[3]), "r"(p));
}
__device__ __forceinline__ void mma_h(float (&d)[4], const uint32_t (&a)[4], uint32_t b0, uint32_t b1) {
  asm volatile("mma.sync.aligned.m16n8k16.row.col.f32.f16.f16.f32 {%0,%1,%2,%3},{%4,%5,%6,%7},{%8,%9},{%0,%1,%2,%3};"
               : "+f"(d[0]), "+f"(d[1]), "+f"(d[2]), "+f"(d[3]) : "r"(a[0]), "r"(a[1]), "r"(a[2]), "r"(a[3]), "r"(b0), "r"(b1));
}
__device__ __forceinline__ void mma_k8(float* d, uint32_t a0, uint32_t a1, uint32_t b0) {
  asm volatile("mma.sync.aligned.m16n8k8.row.col.f32.bf16.bf16.f32 {%0,%1,%2,%3},{%4,%5},{%6},{%0,%1,%2,%3};"
               : "+f"(d[0]), "+f"(d[1]), "+f"(d[2]), "+f"(d[3]) : "r"(a0), "r"(a1), "r"(b0));
}
__device__ __forceinline__ void mma0(float& d0, float& d1, float& d2, float& d3, uint32_t a0, uint32_t a1, uint32_t a2,
                                     uint32_t a3, uint32_t b0, uint32_t b1) {
  asm volatile("mma.sync.aligned.m16n8k16.row.col.f32.bf16.bf16.f32 {%0,%1,%2,%3},{%4,%5,%6,%7},{%8,%9},{%10,%10,%10,%10};"
               : "=f"(d0), "=f"(d1), "=f"(d2), "=f"(d3)
               : "r"(a0), "r"(a1), "r"(a2), "r"(a3), "r"(b0), "r"(b1), "f"(0.f));
}
__device__ __forceinline__ uint32_t pack_bf(float lo, float hi) {
  uint32_t r;
  asm("cvt.rn.bf16x2.f32 %0, %1, %2;" : "=r"(r) : "f"(hi), "f"(lo));
  return r;
}
__device__ __forceinline__ float bf_lo(uint32_t w) { return __uint_as_float(w << 16); }
__device__ __forceinline__ float bf_hi(uint32_t w) { return __uint_as_float(w & 0xffff0000u); }
__device__ __forceinline__ float bf_round(float x) { return __bfloat162float(__float2bfloat16_rn(x)); }
__device__ __forceinline__ uint32_t bmax2(uint32_t a, uint32_t b) {
  uint32_t r; asm("max.bf16x2 %0, %1, %2;" : "=r"(r) : "r"(a), "r"(b)); return r;
}
__device__ __forceinline__ uint32_t bmin2(uint32_t a, uint32_t b) {
  uint32_t r; asm("min.bf16x2 %0, %1, %2;" : "=r"(r) : "r"(a), "r"(b)); return r;
}
__device__ __forceinline__ float ex2(float x) { float r; asm("ex2.approx.ftz.f32 %0, %1;" : "=f"(r) : "f"(x)); return r; }
__device__ __forceinline__ float rcp(float x) { float r; asm("rcp.approx.ftz.f32 %0, %1;" : "=f"(r) : "f"(x)); return r; }
__device__ __forceinline__ void ldsm4(uint32_t (&r)[4], uint32_t a) {
  asm volatile("ldmatrix.sync.aligned.m8n8.x4.shared.b16 {%0,%1,%2,%3}, [%4];"
               : "=r"(r[0]), "=r"(r[1]), "=r"(r[2]), "=r"(r[3]) : "r"(a) : "memory");
}
__device__ __forceinline__ void ldsm4t(uint32_t (&r)[4], uint32_t a) {
  asm volatile("ldmatrix.sync.aligned.m8n8.x4.trans.shared.b16 {%0,%1,%2,%3}, [%4];"
               : "=r"(r[0]), "=r"(r[1]), "=r"(r[2]), "=r"(r[3]) : "r"(a) : "memory");
}
__device__ __forceinline__ void stsm4(uint32_t a, uint32_t r0, uint32_t r1, uint32_t r2, uint32_t r3) {
  asm volatile("stmatrix.sync.aligned.m8n8.x4.shared.b16 [%0], {%1,%2,%3,%4};"
               ::"r"(a), "r"(r0), "r"(r1), "r"(r2), "r"(r3) : "memory");
}
__device__ __forceinline__ uint32_t lds32(uint32_t a) {
  uint32_t r; asm volatile("ld.shared.u32 %0, [%1];" : "=r"(r) : "r"(a) : "memory"); return r;
}
__device__ __forceinline__ uint32_t lds16(uint32_t a) {
  uint32_t r; asm volatile("{\n.reg .u16 h;\nld.shared.u16 h, [%1];\ncvt.u32.u16 %0, h;\n}\n" : "=r"(r) : "r"(a) : "memory"); return r;
}
__device__ __forceinline__ uint2 lds64(uint32_t a) {
  uint2 r; asm volatile("ld.shared.v2.u32 {%0,%1}, [%2];" : "=r"(r.x), "=r"(r.y) : "r"(a) : "memory"); return r;
}
__device__ __forceinline__ uint4 lds128(uint32_t a) {
  uint4 r;
  asm volatile("ld.shared.v4.u32 {%0,%1,%2,%3}, [%4];" : "=r"(r.x), "=r"(r.y), "=r"(r.z), "=r"(r.w) : "r"(a) : "memory");
  return r;
}
__device__ __forceinline__ void sts32(uint32_t a, uint32_t v) { asm volatile("st.shared.u32 [%0], %1;" ::"r"(a), "r"(v) : "memory"); }
__device__ __forceinline__ void sts16(uint32_t a, uint32_t v) {
  asm volatile("{\n.reg .u16 h;\ncvt.u16.u32 h, %1;\nst.shared.u16 [%0], h;\n}\n" ::"r"(a), "r"(v) : "memory");
}
__device__ __forceinline__ void sts64(uint32_t a, uint32_t x, uint32_t y) {
  asm volatile("st.shared.v2.u32 [%0], {%1,%2};" ::"r"(a), "r"(x), "r"(y) : "memory");
}
__device__ __forceinline__ void sts128(uint32_t a, uint32_t x, uint32_t y, uint32_t z, uint32_t w) {
  asm volatile("st.shared.v4.u32 [%0], {%1,%2,%3,%4};" ::"r"(a), "r"(x), "r"(y), "r"(z), "r"(w) : "memory");
}
__device__ __forceinline__ uint4 ld_x(const uint4* p) {
  uint4 r;
  asm volatile("{\n.reg .b128 t;\nld.relaxed.gpu.global.b128 t, [%4];\nmov.b128 {%0,%1,%2,%3}, t;\n}\n"
               : "=r"(r.x), "=r"(r.y), "=r"(r.z), "=r"(r.w) : "l"(p) : "memory");
  return r;
}
__device__ __forceinline__ uint32_t ld_x32(const uint32_t* p) {
  uint32_t r; asm volatile("ld.relaxed.gpu.global.u32 %0, [%1];" : "=r"(r) : "l"(p) : "memory"); return r;
}
__device__ __forceinline__ void st_x(uint4* p, uint32_t x, uint32_t y, uint32_t z, uint32_t w) {
  asm volatile("{\n.reg .b128 t;\nmov.b128 t, {%1,%2,%3,%4};\nst.relaxed.gpu.global.b128 [%0], t;\n}\n"
               ::"l"(p), "r"(x), "r"(y), "r"(z), "r"(w) : "memory");
}
__device__ __forceinline__ void st_x_p(int p, uint4* a, uint32_t x, uint32_t y, uint32_t z, uint32_t w) {
  asm volatile("{\n.reg .b128 t;\n.reg .pred q;\nsetp.ne.b32 q, %5, 0;\nmov.b128 t, {%1,%2,%3,%4};\n@q st.relaxed.gpu.global.b128 [%0], t;\n}\n"
               ::"l"(a), "r"(x), "r"(y), "r"(z), "r"(w), "r"(p) : "memory");
}
__device__ __forceinline__ void sts64_p(int p, uint32_t a, uint32_t x, uint32_t y) {
  asm volatile("{\n.reg .pred q;\nsetp.ne.b32 q, %3, 0;\n@q st.shared.v2.u32 [%0], {%1,%2};\n}\n" ::"r"(a), "r"(x), "r"(y), "r"(p) : "memory");
}
__device__ __forceinline__ void st_x32(uint32_t* p, uint32_t x) {
  asm volatile("st.relaxed.gpu.global.u32 [%0], %1;" ::"l"(p), "r"(x) : "memory");
}
__device__ __forceinline__ uint32_t nz(uint32_t w) { return max(w, 1u); }
__device__ __forceinline__ uint32_t fu(float x) { return __float_as_uint(x); }
__device__ __forceinline__ float uf(uint32_t x) { return __uint_as_float(x); }

__device__ __forceinline__ void wgmma_ss_n96(float (&d)[48], uint64_t da, uint64_t db, int sc) {
  asm volatile("{\n.reg .pred p;\nsetp.ne.b32 p, %50, 0;\n"
      "wgmma.mma_async.sync.aligned.m64n96k16.f32.bf16.bf16 "
      "{%0,%1,%2,%3,%4,%5,%6,%7,%8,%9,%10,%11,%12,%13,%14,%15,%16,%17,%18,%19,%20,%21,%22,%23,%24,%25,%26,%27,%28,%29,%30,%31,%32,%33,%34,%35,%36,%37,%38,%39,%40,%41,%42,%43,%44,%45,%46,%47}, "
      "%48, %49, p, 1, 1, 0, 1;\n}\n"
      : "+f"(d[0]), "+f"(d[1]), "+f"(d[2]), "+f"(d[3]), "+f"(d[4]), "+f"(d[5]), "+f"(d[6]), "+f"(d[7]),
        "+f"(d[8]), "+f"(d[9]), "+f"(d[10]), "+f"(d[11]), "+f"(d[12]), "+f"(d[13]), "+f"(d[14]), "+f"(d[15]),
        "+f"(d[16]), "+f"(d[17]), "+f"(d[18]), "+f"(d[19]), "+f"(d[20]), "+f"(d[21]), "+f"(d[22]), "+f"(d[23]),
        "+f"(d[24]), "+f"(d[25]), "+f"(d[26]), "+f"(d[27]), "+f"(d[28]), "+f"(d[29]), "+f"(d[30]), "+f"(d[31]),
        "+f"(d[32]), "+f"(d[33]), "+f"(d[34]), "+f"(d[35]), "+f"(d[36]), "+f"(d[37]), "+f"(d[38]), "+f"(d[39]),
        "+f"(d[40]), "+f"(d[41]), "+f"(d[42]), "+f"(d[43]), "+f"(d[44]), "+f"(d[45]), "+f"(d[46]), "+f"(d[47])
      : "l"(da), "l"(db), "r"(sc));
}

__device__ __forceinline__ void wgmma_ss_n128(float (&d)[64], uint64_t da, uint64_t db, int sc) {
  asm volatile("{\n.reg .pred p;\nsetp.ne.b32 p, %66, 0;\n"
      "wgmma.mma_async.sync.aligned.m64n128k16.f32.bf16.bf16 "
      "{%0,%1,%2,%3,%4,%5,%6,%7,%8,%9,%10,%11,%12,%13,%14,%15,%16,%17,%18,%19,%20,%21,%22,%23,%24,%25,%26,%27,%28,%29,%30,%31,%32,%33,%34,%35,%36,%37,%38,%39,%40,%41,%42,%43,%44,%45,%46,%47,%48,%49,%50,%51,%52,%53,%54,%55,%56,%57,%58,%59,%60,%61,%62,%63}, "
      "%64, %65, p, 1, 1, 0, 1;\n}\n"
      : "+f"(d[0]), "+f"(d[1]), "+f"(d[2]), "+f"(d[3]), "+f"(d[4]), "+f"(d[5]), "+f"(d[6]), "+f"(d[7]),
        "+f"(d[8]), "+f"(d[9]), "+f"(d[10]), "+f"(d[11]), "+f"(d[12]), "+f"(d[13]), "+f"(d[14]), "+f"(d[15]),
        "+f"(d[16]), "+f"(d[17]), "+f"(d[18]), "+f"(d[19]), "+f"(d[20]), "+f"(d[21]), "+f"(d[22]), "+f"(d[23]),
        "+f"(d[24]), "+f"(d[25]), "+f"(d[26]), "+f"(d[27]), "+f"(d[28]), "+f"(d[29]), "+f"(d[30]), "+f"(d[31]),
        "+f"(d[32]), "+f"(d[33]), "+f"(d[34]), "+f"(d[35]), "+f"(d[36]), "+f"(d[37]), "+f"(d[38]), "+f"(d[39]),
        "+f"(d[40]), "+f"(d[41]), "+f"(d[42]), "+f"(d[43]), "+f"(d[44]), "+f"(d[45]), "+f"(d[46]), "+f"(d[47]),
        "+f"(d[48]), "+f"(d[49]), "+f"(d[50]), "+f"(d[51]), "+f"(d[52]), "+f"(d[53]), "+f"(d[54]), "+f"(d[55]),
        "+f"(d[56]), "+f"(d[57]), "+f"(d[58]), "+f"(d[59]), "+f"(d[60]), "+f"(d[61]), "+f"(d[62]), "+f"(d[63])
      : "l"(da), "l"(db), "r"(sc));
}

__device__ __forceinline__ void wgmma_ss_n40(float (&d)[20], uint64_t da, uint64_t db, int sc) {
  asm volatile("{\n.reg .pred p;\nsetp.ne.b32 p, %22, 0;\n"
      "wgmma.mma_async.sync.aligned.m64n40k16.f32.bf16.bf16 "
      "{%0,%1,%2,%3,%4,%5,%6,%7,%8,%9,%10,%11,%12,%13,%14,%15,%16,%17,%18,%19}, "
      "%20, %21, p, 1, 1, 1, 1;\n}\n"
      : "+f"(d[0]), "+f"(d[1]), "+f"(d[2]), "+f"(d[3]), "+f"(d[4]), "+f"(d[5]), "+f"(d[6]), "+f"(d[7]),
        "+f"(d[8]), "+f"(d[9]), "+f"(d[10]), "+f"(d[11]), "+f"(d[12]), "+f"(d[13]), "+f"(d[14]), "+f"(d[15]),
        "+f"(d[16]), "+f"(d[17]), "+f"(d[18]), "+f"(d[19])
      : "l"(da), "l"(db), "r"(sc));
}

__device__ __forceinline__ void wgmma_rs_n8(float (&d)[4], const uint4& a, uint64_t db, int sc) {
  asm volatile("{\n.reg .pred p;\nsetp.ne.b32 p, %9, 0;\n"
      "wgmma.mma_async.sync.aligned.m64n8k16.f32.bf16.bf16 "
      "{%0,%1,%2,%3}, "
      "{%4,%5,%6,%7}, %8, p, 1, 1, 1;\n}\n"
      : "+f"(d[0]), "+f"(d[1]), "+f"(d[2]), "+f"(d[3])
      : "r"(a.x), "r"(a.y), "r"(a.z), "r"(a.w), "l"(db), "r"(sc));
}

__device__ __forceinline__ void wgmma_rs_n16(float (&d)[8], const uint4& a, uint64_t db, int sc) {
  asm volatile("{\n.reg .pred p;\nsetp.ne.b32 p, %13, 0;\n"
      "wgmma.mma_async.sync.aligned.m64n16k16.f32.bf16.bf16 "
      "{%0,%1,%2,%3,%4,%5,%6,%7}, "
      "{%8,%9,%10,%11}, %12, p, 1, 1, 1;\n}\n"
      : "+f"(d[0]), "+f"(d[1]), "+f"(d[2]), "+f"(d[3]), "+f"(d[4]), "+f"(d[5]), "+f"(d[6]), "+f"(d[7])
      : "r"(a.x), "r"(a.y), "r"(a.z), "r"(a.w), "l"(db), "r"(sc));
}

__device__ __forceinline__ void wgmma_rs_n24(float (&d)[12], const uint4& a, uint64_t db, int sc) {
  asm volatile("{\n.reg .pred p;\nsetp.ne.b32 p, %17, 0;\n"
      "wgmma.mma_async.sync.aligned.m64n24k16.f32.bf16.bf16 "
      "{%0,%1,%2,%3,%4,%5,%6,%7,%8,%9,%10,%11}, "
      "{%12,%13,%14,%15}, %16, p, 1, 1, 1;\n}\n"
      : "+f"(d[0]), "+f"(d[1]), "+f"(d[2]), "+f"(d[3]), "+f"(d[4]), "+f"(d[5]), "+f"(d[6]), "+f"(d[7]),
        "+f"(d[8]), "+f"(d[9]), "+f"(d[10]), "+f"(d[11])
      : "r"(a.x), "r"(a.y), "r"(a.z), "r"(a.w), "l"(db), "r"(sc));
}

struct Params {
  const __nv_bfloat16 *logA, *Aim, *Cre, *Cim, *logdt, *Dskip, *x, *wphi, *wo;
  __nv_bfloat16* out;
  uint4* xs;
  long long* ts;
};

__device__ __forceinline__ uint4 tr_row(const uint4 (&v)[8], int i) {
  uint32_t o[4];
#pragma unroll
  for (int m = 0; m < 4; m++) {
    const uint4 &ra = v[2 * m], &rb = v[2 * m + 1];
    const int k = i >> 1;
    const uint32_t xa = k == 0 ? ra.x : k == 1 ? ra.y : k == 2 ? ra.z : ra.w;
    const uint32_t xb = k == 0 ? rb.x : k == 1 ? rb.y : k == 2 ? rb.z : rb.w;
    o[m] = __byte_perm(xa, xb, (i & 1) ? 0x7632 : 0x5410);
  }
  return make_uint4(o[0], o[1], o[2], o[3]);
}

struct cpx { float r, i; };
__device__ __forceinline__ cpx csq(cpx a) { return {a.r * a.r - a.i * a.i, 2.f * (a.r * a.i)}; }
__device__ __forceinline__ cpx polar(float e, float t) {
  const float m = ex2(e);
  return {m * __cosf(t), m * __sinf(t)};
}

struct KgenRaw { unsigned short la, ai, cr, ci, ldt; };
__device__ __forceinline__ KgenRaw kgen_load(const Params& P, int d, int unit, int lane) {
  const int o = d * 128 + unit * 32 + lane;
  return {__ldg((const unsigned short*)P.logA + o), __ldg((const unsigned short*)P.Aim + o), __ldg((const unsigned short*)P.Cre + o),
          __ldg((const unsigned short*)P.Cim + o), __ldg((const unsigned short*)P.logdt + d)};
}
struct hmul { __half2 a, b; };
__device__ __forceinline__ hmul mk_mul(cpx w) {
  uint32_t b;
  asm("{\n.reg .f32 n;\nneg.ftz.f32 n, %1;\ncvt.rn.f16x2.f32 %0, %2, n;\n}\n" : "=r"(b) : "f"(w.i), "f"(w.r));
  return {__floats2half2_rn(w.r, w.i), *(const __half2*)&b};
}
__device__ __forceinline__ __half2 hcm(__half2 z, const hmul& w) { return __hfma2(__high2half2(z), w.b, __hmul2(__low2half2(z), w.a)); }
__device__ __forceinline__ uint32_t hu(__half2 v) { return *(const uint32_t*)&v; }

struct KgenAddr { uint32_t sa, lb, lm[4]; };
__device__ __forceinline__ KgenAddr kgen_addr(int lane, uint32_t buf) {
  KgenAddr a;
  a.sa = buf + (lane & 7) * 128 + ((((lane >> 3) ^ lane) & 7) << 4);
  const int q = lane >> 3;
  a.lb = buf + q * 128 + (((lane ^ q) & 7) << 4);
  a.lm[0] = buf + q * 128 + (q << 4);
  a.lm[1] = buf + q * 128 + ((1 ^ q) << 4);
  a.lm[2] = buf + q * 128 + (((2 + (lane & 1)) ^ q) << 4);
  a.lm[3] = buf + q * 128 + (((4 + (lane & 3)) ^ q) << 4);
  asm volatile("" : "+r"(a.sa), "+r"(a.lb), "+r"(a.lm[0]), "+r"(a.lm[1]), "+r"(a.lm[2]), "+r"(a.lm[3]));
  return a;
}
__device__ __forceinline__ void kgen_unit(const KgenRaw& r, const KgenAddr& ad, uint32_t zero, float (&k)[5][4], float& k2048, float& sc) {
  const float dt = bf_round(expf(bf_lo(r.ldt)));
  const float a2 = bf_round(ex2(bf_lo(r.la) * 1.4426950408889634f)) * (dt * -1.4426950408889634f);
  const float f = bf_lo(r.ai) * dt;
  const float r127 = f * 20.21267777267071f;
  const uint32_t ex = min(max(__reduce_max_sync(0xffffffffu, max(r.cr & 0x7fffu, r.ci & 0x7fffu)) >> 7, 1u), 253u);
  const float cs = uf((254u - ex) << 23);
  sc = 2.f * dt * uf(ex << 23);
  const cpx C = {bf_lo(r.cr) * cs, -bf_lo(r.ci) * cs};
  auto put = [&](const __half2 (&v)[8]) {
    stsm4(ad.sa, hu(v[0]), hu(v[1]), hu(v[2]), hu(v[3]));
    stsm4(ad.sa ^ 64, hu(v[4]), hu(v[5]), hu(v[6]), hu(v[7]));
    __syncwarp();
  };
  auto get = [&](uint32_t (&o)[2][4], uint32_t a) { ldsm4(o[0], a); ldsm4(o[1], (a ^ 64) + 512); };
  auto rot = [](uint32_t z) { return __byte_perm(z, z, 0x1032) ^ 0x8000u; };
  auto fmul = [](uint32_t z, uint32_t zi, uint32_t w) {
    const __half2 hw = *(const __half2*)&w;
    return hu(__hfma2(*(const __half2*)&zi, __high2half2(hw), __hmul2(*(const __half2*)&z, __low2half2(hw))));
  };
  uint32_t A[4][4];
  auto tile = [&](int j, const uint32_t (&B)[2][4]) {
    k[j][0] = k[j][1] = k[j][2] = k[j][3] = 0.f;
#pragma unroll
    for (int s = 0; s < 4; s++) mma_h(k[j], A[s], B[s >> 1][2 * (s & 1)], B[s >> 1][2 * (s & 1) + 1]);
  };
  auto after = [&](cpx v, uint32_t dep) { return cpx{uf(fu(v.r) ^ (dep & zero)), v.i}; };
  const cpx w1 = polar(a2, f), w127 = polar(a2 * 127.f, (r127 - rintf(r127)) * 6.283185307179586f);
  const cpx w2 = csq(w1), w4 = csq(w2);
  uint32_t T0[2][4], A0[2][4], T4[2][4], M[4][2][4];
  {
    __half2 t[8];
    const hmul m2 = mk_mul(w2), m4 = mk_mul(w4);
    t[0] = __floats2half2_rn(1.f, 0.f); t[1] = __floats2half2_rn(w1.r, w1.i); t[2] = m2.a; t[4] = m4.a;
    t[3] = hcm(t[1], m2); t[5] = hcm(t[1], m4); t[6] = hcm(t[2], m4); t[7] = hcm(t[3], m4);
    put(t); get(T0, ad.lb);
  }
  cpx w8 = csq(w4);
  w8.i = -w8.i;
  const cpx w16 = csq(w8), w32 = csq(w16), w64 = csq(w32);
  {
    const hmul m8 = mk_mul(w8), m16 = mk_mul(w16), m32 = mk_mul(w32);
    __half2 a[8];
    a[0] = __floats2half2_rn(C.r, C.i); a[1] = hcm(a[0], m8);
    a[2] = hcm(a[0], m16); a[3] = hcm(a[1], m16);
#pragma unroll
    for (int i = 0; i < 4; i++) a[4 + i] = hcm(a[i], m32);
    put(a); get(A0, ad.lb);
  }
  const cpx w127b = after(w127, T0[0][0]);
  const cpx w128 = {w127b.r * w1.r - w127b.i * w1.i, w127b.r * w1.i + w127b.i * w1.r};
  const cpx w256 = csq(w128), w512 = csq(w256);
  const hmul m128 = mk_mul(w128), m256 = mk_mul(w256), m512 = mk_mul(w512);
  {
    const hmul m254 = mk_mul(csq(w127b));
    const __half2 h127 = __floats2half2_rn(w127b.r, w127b.i);
    __half2 m[8];
    m[0] = __floats2half2_rn(w64.r, w64.i); m[1] = m128.a; m[2] = m256.a; m[3] = hcm(h127, m256);
    m[4] = m512.a; m[5] = hcm(h127, m512); m[6] = hcm(m[4], m254); m[7] = hcm(m[5], m254);
    put(m);
#pragma unroll
    for (int i = 0; i < 4; i++) get(M[i], ad.lm[i]);
  }
  const cpx w1024 = csq(after(w512, A0[0][0])), we = csq(w1024);
  {
    __half2 t[8];
    t[0] = __floats2half2_rn(w1024.r, w1024.i); t[1] = hcm(t[0], m128);
    t[2] = hcm(t[0], m256); t[3] = hcm(t[1], m256);
#pragma unroll
    for (int i = 0; i < 4; i++) t[4 + i] = hcm(t[i], m512);
    put(t); get(T4, ad.lb);
  }
  k2048 = (C.r * we.r + C.i * we.i) * sc;
#pragma unroll
  for (int i = 0; i < 8; i++) {
    const uint32_t z = A0[i >> 2][i & 3];
    A[i >> 1][2 * (i & 1)] = z;
    A[i >> 1][2 * (i & 1) + 1] = fmul(z, rot(z), M[0][i >> 2][i & 3]);
  }
  tile(0, T0);
#pragma unroll
  for (int i = 0; i < 8; i++) {
    const uint32_t z = T0[i >> 2][i & 3], zi = rot(z);
#pragma unroll
    for (int j = 1; j < 4; j++) M[j][i >> 2][i & 3] = fmul(z, zi, M[j][i >> 2][i & 3]);
  }
  tile(4, T4); tile(1, M[1]); tile(2, M[2]); tile(3, M[3]);
}

__device__ __forceinline__ void build_tables(uint32_t tb, int lane, float (&k)[5][4], float k2048) {
  const int g = lane >> 2, c = lane & 3;
  const uint32_t kc = tb + T_KC + 16;
  {
    const uint32_t a0 = kc + 16 * g + 4 * c, a2 = kc + 2 * (256 + 4 * g + c);
    const uint32_t a3 = kc + 2 * (384 + 2 * g + 64 * (c & 1) + (c >> 1)), a4 = kc + 2 * (512 + g + 32 * c);
#pragma unroll
    for (int r = 0; r < 2; r++) {
      sts32(a0 + 128 * r, pack_bf(k[0][2 * r], k[0][2 * r + 1]));
      sts32(a0 + 128 * r + 256, pack_bf(k[1][2 * r], k[1][2 * r + 1]));
      const uint32_t w2 = pack_bf(k[2][2 * r], k[2][2 * r + 1]);
      const uint32_t w3 = pack_bf(k[3][2 * r], k[3][2 * r + 1]);
      const uint32_t w4 = pack_bf(k[4][2 * r], k[4][2 * r + 1]);
      sts16(a2 + 64 * r, w2); sts16(a2 + 64 * r + 128, w2 >> 16);
      sts16(a3 + 32 * r, w3); sts16(a3 + 32 * r + 64, w3 >> 16);
      sts16(a4 + 16 * r, w4); sts16(a4 + 16 * r + 32, w4 >> 16);
    }
  }
  if (lane == 0) { sts16(kc + 2 * 640, pack_bf(k2048, 0.f)); sts32(kc - 4, 0); }
  __syncwarp();
  const uint32_t td = tb + T_D + 32;
#pragma unroll
  for (int hf = 0; hf < 2; hf++) {
    const uint2 v = lds64(kc + 256 * hf + 8 * lane);
    const uint32_t pv = lds32(kc + 256 * hf + 8 * lane - 4);
    sts128(td + 512 * hf + 16 * lane, __byte_perm(v.x, pv, 0x7610), __byte_perm(v.x, v.x, 0x1032), __byte_perm(v.y, v.x, 0x7610),
           __byte_perm(v.y, v.y, 0x1032));
  }
#pragma unroll
  for (int hf = 0; hf < 2; hf++) {
    const uint32_t v = lds32(kc + 512 + 128 * hf + 4 * lane), nx = lds32(kc + 516 + 128 * hf + 4 * lane);
    uint32_t w0 = __byte_perm(v, v, 0x1010);
    const uint32_t w1 = w0;
    if (hf == 0) { const uint32_t pv = lds32(kc + 508); if (lane == 0) w0 = __byte_perm(v, pv, 0x7610); }
    sts128(td + 1024 + 512 * hf + 16 * lane, w0, w1, __byte_perm(v, v, 0x1032), __byte_perm(nx, v, 0x7610));
  }
  {
    const uint32_t kk = lds16(kc + 2 * 384);
    const uint32_t w = lane < 3 ? (kk | (kk << 16)) : (lane == 3 ? (kk << 16) : 0u);
    if (lane < 24) sts32(td + 4 * (lane < 16 ? 512 + lane : lane - 24), w);
    const uint32_t lo_ = lds16(kc + 2 * 511), le_ = lds16(kc + 2 * 512);
    const uint32_t ja = tb + T_5 + (lane < 16 ? 4 * lane : 256 + 4 * lane);
    sts32(ja, lane == 16 ? (le_ << 16) : 0u);
    sts32(ja + 384, lane == 16 ? (lo_ << 16) : 0u);
    sts32(tb + (lane < 16 ? T_7 : T_9 - 64) + 4 * lane, 0u);
  }
#pragma unroll
  for (int s = 0; s < 2; s++) {
    const uint32_t b = kc + 2 * (s ? 512 : 384) + 8 * lane;
    const uint2 v = lds64(b);
    uint32_t em = lds16(b - 2), e0 = v.x;
    const uint32_t e4 = lds16(b + 8);
    if (lane == 0) { em = 0; e0 = 0; }
    sts64(tb + (s ? T_7 : T_3) + 64 + 8 * lane, __byte_perm(v.x, em, 0x5432), __byte_perm(v.y, v.x, 0x7632));
    sts64(tb + (s ? T_9 : T_5) + 64 + 8 * lane, __byte_perm(v.y, e0, 0x5410), __byte_perm(e4, v.y, 0x5410));
  }
  __syncwarp();
}

__device__ __forceinline__ uint32_t box2w(int lo, int n, int o) {
  return ((unsigned)(o - lo) < (unsigned)n ? 0x3F80u : 0u) | ((unsigned)(o + 1 - lo) < (unsigned)n ? 0x3F800000u : 0u);
}

__device__ __forceinline__ void conv_channel(uint32_t ub, uint32_t tb, int lane, uint4* ydst) {
  const int g = lane >> 2, c = lane & 3, x = g - 2 * c;
  const int mi = lane >> 3;
  const uint32_t qa = ub + U_PAD + 16 * (lane & 7) + ((mi == 0 || mi == 3) ? U_ODD : 0) - (mi == 0 ? 16 : 0);
  const uint32_t hb = ub + U_PAD + (mi & 1) * U_ODD + 16 * ((lane >> 4) + (lane & 7)) - 16;
  const uint32_t kv = lds16(tb + T_KC + 16 + 2 * 512);
  const int oh = c < 2 ? 8 + 2 * c : 2 * c - 8, og = c < 3 ? 2 * c : -10;
  uint32_t bx[4] = {box2w(g - 4, 9, 2 * c), box2w(g - 3, 7, 2 * c), box2w(g - 4, 9, oh), box2w(g - 3, 7, oh)};
  uint32_t by[4] = {box2w(g - 10, 5, 2 * c - 8), box2w(g - 5, 3, 2 * c - 8), box2w(g - 10, 5, og), box2w(g - 5, 3, og)};
  uint32_t lb0 = ((unsigned)(x + 5) < 2u ? kv : 0u) | ((unsigned)(x + 4) < 2u ? kv << 16 : 0u);
  uint32_t lb1 = ((unsigned)(x - 3) < 2u ? kv : 0u) | ((unsigned)(x - 4) < 2u ? kv << 16 : 0u);
  const int q0 = g - 1, q1 = c < 3 ? g : g - 2;
  uint32_t y0a = ub + U_PAD + (q0 & 1) * U_ODD + 16 * (q0 >> 1) + 4 * c;
  uint32_t y1a = ub + U_PAD + (q1 & 1) * U_ODD + 16 * (q1 >> 1) + 4 * c;
#pragma unroll
  for (int i = 0; i < 4; i++) asm volatile("" : "+r"(bx[i]), "+r"(by[i]));
  asm volatile("" : "+r"(lb0), "+r"(lb1), "+r"(y0a), "+r"(y1a));
  mbar_wait(BAR(MB_UFULL));
  mbar_spin(BAR(MB_EMPTY + 15));
  nb_sync(NB_GATE, 256);
  SPLIT();
  TS(36);
  float acc[16][4];
  {
    uint32_t z09[8], z07[8], zm9[8], zm7[8];
#pragma unroll
    for (int i = 0; i < 8; i++) {
      uint32_t h[4];
      ldsm4(h, hb + 128 * i);
      float y0, y1, y2, y3, w0, w1, w2, w3;
      mma0(y0, y1, y2, y3, bx[0], bx[1], bx[2], bx[3], h[2], c < 2 ? h[3] : h[1]);
      mma0(w0, w1, w2, w3, bx[0], bx[1], bx[2], bx[3], h[1], c < 2 ? h[2] : h[0]);
      z09[i] = pack_bf(y0, y1); z07[i] = pack_bf(y2, y3);
      zm9[i] = pack_bf(w0, w1); zm7[i] = pack_bf(w2, w3);
    }
  uint32_t f3[3][4][4];
  {
    const uint32_t fa = tb + T_7 + 4 * (16 + x);
#pragma unroll
    for (int tt = 0; tt < 3; tt++)
#pragma unroll
      for (int D = 0; D < 4; D++) {
        const uint32_t a = fa + (tt == 0 ? 316 : (tt == 1 ? 320 : 0)) + 64 * D;
        f3[tt][D][0] = lds32(a); f3[tt][D][1] = lds32(a + 32); f3[tt][D][2] = lds32(a - 32); f3[tt][D][3] = lds32(a);
      }
  }
    float a[4][2][4];
#pragma unroll
    for (int kap = 0; kap < 4; kap++)
#pragma unroll
      for (int sg = 0; sg < 2; sg++)
#pragma unroll
        for (int bk = 3; bk >= kap; bk--) {
          const uint32_t(&q0_)[4] = f3[sg ? 2 : 0][bk - kap];
          const uint32_t(&q1_)[4] = f3[sg ? 2 : 1][bk - kap];
          float(&a0)[4] = a[bk][0];
          float(&a1)[4] = a[bk][1];
          if (sg == 0 && kap == 0) {
            mma0(a0[0], a0[1], a0[2], a0[3], q0_[0], q0_[1], q0_[2], q0_[3], z09[0], z09[1]);
            mma0(a1[0], a1[1], a1[2], a1[3], q1_[0], q1_[1], q1_[2], q1_[3], zm9[0], zm9[1]);
          } else {
            mma(a0[0], a0[1], a0[2], a0[3], q0_[0], q0_[1], q0_[2], q0_[3], sg ? zm7[2 * kap] : z09[2 * kap], sg ? zm7[2 * kap + 1] : z09[2 * kap + 1]);
            mma(a1[0], a1[1], a1[2], a1[3], q1_[0], q1_[1], q1_[2], q1_[3], sg ? z07[2 * kap] : zm9[2 * kap], sg ? z07[2 * kap + 1] : zm9[2 * kap + 1]);
          }
        }
    SPLIT();
#pragma unroll
    for (int i = 0; i < 8; i++) {
      uint32_t h[4];
      ldsm4(h, qa + 128 * i);
      const float ci[4] = {a[i >> 1][0][2 * (i & 1)], a[i >> 1][0][2 * (i & 1) + 1], a[i >> 1][1][2 * (i & 1)], a[i >> 1][1][2 * (i & 1) + 1]};
      mmac(acc[8 + i], h[0], h[1], h[2], h[3], lb0, lb1, ci);
    }
  }
  TS(44);
  {
    uint2 a5[10], a3[10];
    const uint32_t aa = tb + T_5 + 4 * (8 + 2 * g - 2 * c);
#pragma unroll
    for (int m = 0; m < 10; m++) { a5[m] = lds64(aa + 32 * m); a3[m] = lds64(aa + 384 + 32 * m); }
    uint32_t x5[12][2], x3[12][2];
    auto ygen = [&](int kap) {
#pragma unroll
      for (int hh = 0; hh < 2; hh++) {
        float y0, y1, y2, y3;
        mma0(y0, y1, y2, y3, by[0], by[1], by[2], by[3], lds32(y0a + 128 * kap + 64 * hh), lds32(y1a + 128 * kap + 64 * hh));
        x5[kap][hh] = pack_bf(y0, y1);
        x3[kap][hh] = pack_bf(y2, y3);
      }
    };
    ygen(11); ygen(10); ygen(9); ygen(8);
#pragma unroll
    for (int kap = 11; kap >= 0; kap--) {
      if (kap >= 4) ygen(kap - 4);
#pragma unroll
      for (int sg = 0; sg < 2; sg++)
#pragma unroll
        for (int i = 4; i >= 0; i--) {
          const int be = kap + 4 + i;
          if (be <= 15) {
            const uint2 &hi = sg ? a3[2 * i + 1] : a5[2 * i + 1], &lo = sg ? a3[2 * i] : a5[2 * i];
            const uint32_t b0 = sg ? x3[kap][0] : x5[kap][0], b1 = sg ? x3[kap][1] : x5[kap][1];
            if (be < 8 && i == 0 && sg == 0) mma0(acc[be][0], acc[be][1], acc[be][2], acc[be][3], hi.x, hi.y, lo.x, lo.y, b0, b1);
            else mma(acc[be][0], acc[be][1], acc[be][2], acc[be][3], hi.x, hi.y, lo.x, lo.y, b0, b1);
          }
        }
    }
  }
  TS(45);
  {
    const uint32_t st = tb + T_ST + lane * 8;
#pragma unroll
    for (int be = 4; be < 12; be++) sts64(st + 256 * be, pack_bf(acc[be][0], acc[be][1]), pack_bf(acc[be][2], acc[be][3]));
    SPLIT();
    uint32_t F[66], qd[8][4];
    const uint32_t fa = tb + T_D + 32 + 4 * x;
#pragma unroll
    for (int i = 0; i < 32; i++) {
      const int s = 120 - (i >> 2) - 8 * (i & 3);
      uint32_t(&q)[4] = qd[i & 7];
      ldsm4(q, qa + 16 * s);
      const int m = 16 * (i & 3) + 2 * (i >> 2);
      F[m] = lds32(fa + 32 * m); F[m + 1] = lds32(fa + 32 * m + 32);
#pragma unroll
      for (int be = 15; be >= 12; be--) {
        const int de = 8 * be - s;
        float(&a)[4] = (be >= 14 && !(i & 1)) ? acc[be - 4] : acc[be];
        if (de >= 0 && be >= 14 && i == 2 * (15 - be)) mma0(a[0], a[1], a[2], a[3], q[0], q[1], q[2], q[3], F[2 * de + 1], F[2 * de]);
        else if (de >= 0) mma(a[0], a[1], a[2], a[3], q[0], q[1], q[2], q[3], F[2 * de + 1], F[2 * de]);
      }
    }
#pragma unroll
    for (int i = 0; i < 8; i++) acc[14 + (i >> 2)][i & 3] += acc[10 + (i >> 2)][i & 3];
    F[64] = lds32(fa + 32 * 64); F[65] = lds32(fa + 32 * 65);
    uint32_t qp = qa + 128 * 11, sta = st + 256 * 10;
    uint4* yd = ydst + 7 * 32;
#pragma unroll
    for (int i = 0; i < 6; i++) ldsm4(qd[i], qp - 16 * i);
    uint2 sv = lds64(sta + 256);
    float ci[4] = {bf_lo(sv.x), bf_hi(sv.x), bf_lo(sv.y), bf_hi(sv.y)};
    float T[5][4];
#pragma unroll
    for (int i = 0; i < 16; i++) T[i >> 2][i & 3] = acc[12 + (i >> 2)][i & 3];
    nb_sync(NB_YZ, 160);
    TS(46);
#pragma unroll 1
    for (int bp = 5; bp >= 0; bp--) {
      uint32_t held[2];
#pragma unroll
      for (int o = 1; o >= 0; o--) {
#pragma unroll
        for (int k = 4; k >= 1; k--) mmac(T[k], qd[0][0], qd[0][1], qd[0][2], qd[0][3], F[16 * k + 1], F[16 * k], T[k - 1]);
        mmac(T[0], qd[0][0], qd[0][1], qd[0][2], qd[0][3], F[1], F[0], ci);
        ldsm4(qd[6], qp - 16 * 6);
        ldsm4(qd[7], qp - 16 * 7);
        sv = lds64(sta);
#pragma unroll
        for (int i = 1; i < 8; i++) {
#pragma unroll
          for (int k = 3; k >= 0; k--)
            mma(T[k][0], T[k][1], T[k][2], T[k][3], qd[i][0], qd[i][1], qd[i][2], qd[i][3], F[16 * k + 2 * i + 1], F[16 * k + 2 * i]);
          if (i < 7) ldsm4(qd[i - 1], qp - 128 - 16 * (i - 1));
          if (i == 2) {
            const uint32_t w0 = pack_bf(T[4][0], T[4][1]), w1 = pack_bf(T[4][2], T[4][3]);
            if (o) { held[0] = w0; held[1] = w1; }
            else st_x(yd, nz(w0), w1, held[0], held[1]);
          }
          if (i == 4) {
            if (2 * bp + o <= 4) sv = make_uint2(0, 0);
            ci[0] = bf_lo(sv.x); ci[1] = bf_hi(sv.x); ci[2] = bf_lo(sv.y); ci[3] = bf_hi(sv.y);
          }
        }
        qp -= 128; sta -= 256;
      }
      yd -= 32;
      if (!(bp & 1)) nb_arrive(NB_Y + 1 + (bp >> 1), 160);
    }
#pragma unroll
    for (int B = 1; B >= 0; B--)
      st_x(ydst + B * 32, nz(pack_bf(T[2 * B][0], T[2 * B][1])), pack_bf(T[2 * B][2], T[2 * B][3]),
           pack_bf(T[2 * B + 1][0], T[2 * B + 1][1]), pack_bf(T[2 * B + 1][2], T[2 * B + 1][3]));
  }
}

__device__ __forceinline__ void dual_exp(const uint32_t* w, uint32_t* e) {
  const float L = 1.44268798828125f;
  uint32_t mx = bmax2(bmax2(w[0], w[1]), bmax2(w[2], w[3]));
  uint32_t mn = bmin2(bmin2(w[0], w[1]), bmin2(w[2], w[3]));
  mx = bmax2(mx, __shfl_xor_sync(0xffffffffu, mx, 1));
  mn = bmin2(mn, __shfl_xor_sync(0xffffffffu, mn, 1));
  mx = bmax2(mx, __shfl_xor_sync(0xffffffffu, mx, 2));
  mn = bmin2(mn, __shfl_xor_sync(0xffffffffu, mn, 2));
  const float mx0 = bf_lo(mx) * -L, mx1 = bf_hi(mx) * -L, mn0 = bf_lo(mn) * L, mn1 = bf_hi(mn) * L;
#pragma unroll
  for (int i = 0; i < 2; i++) {
    const float a0 = bf_lo(w[2 * i]), a1 = bf_hi(w[2 * i]), b0 = bf_lo(w[2 * i + 1]), b1 = bf_hi(w[2 * i + 1]);
    e[2 * i] = pack_bf(ex2(fmaf(a0, L, mx0)), ex2(fmaf(b0, L, mx0)));
    e[2 * i + 1] = pack_bf(ex2(fmaf(a1, L, mx1)), ex2(fmaf(b1, L, mx1)));
    e[4 + 2 * i] = pack_bf(ex2(fmaf(a0, -L, mn0)), ex2(fmaf(b0, -L, mn0)));
    e[5 + 2 * i] = pack_bf(ex2(fmaf(a1, -L, mn1)), ex2(fmaf(b1, -L, mn1)));
  }
}
__device__ __forceinline__ void normalise(uint32_t* e, const float (&s)[4]) {
  const uint32_t r = pack_bf(rcp(s[0]), rcp(s[2]));
  const __nv_bfloat162 rr = *(const __nv_bfloat162*)&r;
#pragma unroll
  for (int i = 0; i < 4; i++) {
    const __nv_bfloat162 v = __hmul2(*(const __nv_bfloat162*)&e[i], (i & 1) ? __high2bfloat162(rr) : __low2bfloat162(rr));
    e[i] = *(const uint32_t*)&v;
  }
}
__host__ __device__ constexpr uint64_t qdesc(uint32_t addr) { return mkdesc(addr, 128, 256, 0); }

__global__ void __launch_bounds__(NTHREADS, 1)
fused_kernel(const Params P, const __grid_constant__ CUtensorMap mx, const __grid_constant__ CUtensorMap mw,
             const __grid_constant__ CUtensorMap mo, const __grid_constant__ CUtensorMap mu,
             const __grid_constant__ CUtensorMap mout, const __grid_constant__ CUtensorMap mw4) {
  constexpr uint32_t sb = SB;
  const int tid = threadIdx.x, lane = tid & 31;
  const int warp = __shfl_sync(0xffffffffu, tid >> 5, 0);
  const int b = blockIdx.x, oct = b >> 3, i8 = b & 7;
  const int rt = (((oct & 4) ? ~oct : oct) & 3) * 2 + (i8 >> 2);
  const int hp = (oct >> 2) * 4 + (i8 & 3);

  const int wg = warp >> 2, w = warp & 3;
  const int d = b * 4 + ((tid >> 5) & 3);
  const KgenRaw raw = kgen_load(P, d, tid >> 7, lane);
  const unsigned short dsk = __ldg((const unsigned short*)P.Dskip + d);
  if (warp == 15) {
    asm volatile("prefetch.tensormap [%0];" ::"l"(&mu) : "memory");
    asm volatile("prefetch.tensormap [%0];" ::"l"(&mw) : "memory");
    asm volatile("prefetch.tensormap [%0];" ::"l"(&mx) : "memory");
    asm volatile("prefetch.tensormap [%0];" ::"l"(&mw4) : "memory");
  }
  if (warp == 12) {
    if (lane == 0) {
#pragma unroll
      for (int i = 0; i < 9; i++) mbar_init(BAR(i), 1);
      asm volatile("fence.mbarrier_init.release.cluster;" ::: "memory");
    }
    __syncwarp();
    if (lane < 9) mbar_expect(BAR(0) + 8 * lane, (lane == 5 || lane == 7) ? 40960 : ((lane == 0 || lane > 5) ? 16384 : 28672));
    __syncwarp();
    e_tma3d(sb + OFF_W, &mw, BAR(MB_FULL), hp * 32, 0, 0);
    e_tma2d(sb + OFF_X + 3 * 16384, &mx, BAR(MB_FULL), 0, rt * 256);
    nb_arrive(NB_PROD, 512);
  } else if (warp == 14) {
    e_prefetch(P.x + (size_t)(rt * 256 + hp * 8) * 512, 8192);
  } else if (warp == 13) {
    if (lane == 0) {
#pragma unroll
      for (int i = 9; i < 40; i++) mbar_init(BAR(i), i < MB_EMPTY ? 1 : 4);
      asm volatile("fence.mbarrier_init.release.cluster;" ::: "memory");
    }
    __syncwarp();
    if (lane < 14 && lane != 9) mbar_expect(BAR(MB_FULL + 8) + 8 * lane, lane == 8 ? 131072 : (lane == 10 ? 8192 : (lane == 13 ? 24576 : 16384)));
    nb_arrive(NB_PROD, 512);
  }
  const uint32_t tb = sb + OFF_T + w * T_CH;
  const uint32_t kp = wg == 2 ? sb + OFF_STG0 + 16384 + w * 1024 : ((tb + 127) & ~127u) + (wg == 3 ? 2 : wg) * 1536;
  const KgenAddr kad = kgen_addr(lane, kp);
  if ((warp >> 1) != 6) nb_sync(NB_PROD, 512);
  else nb_sync(NB_GATE + 1, 64);
  if (warp == 12) {
#pragma unroll 1
    for (int kb = 1; kb < 4; kb++) {
      if (kb == U_AT) e_tma4d(sb + OFF_STG0, &mu, BAR(MB_URAW), i8 * 64, oct * 2);
      e_tma3d(sb + OFF_W + kb * 12288, &mw, BAR(MB_FULL) + 8 * kb, hp * 32, kb * 64, 0);
      e_tma2d(sb + OFF_X + (kb < 2 ? kb + 3 : kb - 2) * 16384, &mx, BAR(MB_FULL) + 8 * kb, kb * 64, rt * 256);
    }
    e_tma4d(sb + OFF_W + 4 * 12288, &mw4, BAR(MB_FULL + 4), hp * 32, 4);
    e_tma2d(sb + OFF_X + 2 * 16384, &mx, BAR(MB_FULL + 4), 256, rt * 256);
    e_tma4d(sb + OFF_W + 6 * 12288, &mw4, BAR(MB_FULL + 6), hp * 32, 6);
    if (smem_u32(smem_raw) != SB) __trap();
    if (lane == 0) TS1(54);
  }
  float k[5][4], k2048, ksc;
  kgen_unit(raw, kad, blockIdx.y, k, k2048, ksc);
  TS(40 + wg);
  if ((fu(k[0][0]) & fu(k[1][0]) & fu(k[2][0]) & fu(k[3][0]) & fu(k[4][0])) == 0xffffffffu) sts32(kp, 0);
  if (wg) nb_arrive(0, 512);
  k2048 += __shfl_xor_sync(0xffffffffu, k2048, 16);
  k2048 += __shfl_xor_sync(0xffffffffu, k2048, 8);
  if (wg != 2) {
    uint32_t h[10];
#pragma unroll
    for (int j = 0; j < 10; j++) h[j] = hu(__floats2half2_rn(k[j >> 1][2 * (j & 1)], k[j >> 1][2 * (j & 1) + 1]));
    sts128(kp + lane * 16, h[0], h[1], h[2], h[3]);
    sts128(kp + 512 + lane * 16, h[4], h[5], h[6], h[7]);
    sts128(kp + 1024 + lane * 16, h[8], h[9], fu(k2048), fu(ksc));
  }
  if (wg == 0) { nb_arrive(NB_PREP, 512); nb_sync(0, 512); }
  else if (wg != 2) nb_arrive(NB_PREP, 512);
  else nb_sync(NB_PREP, 512);
  if (warp >= 12) {
    asm volatile("setmaxnreg.dec.sync.aligned.u32 32;");
    if (warp == 12) {
      if (X2_AT < 0) e_prefetch(P.x + (size_t)(rt * 256 + 128 + hp * 8) * 512, 8192);
      uint32_t slot = sb + OFF_X + 3 * 16384;
#pragma unroll 1
      for (int n = 0; n < 11; n++) {
        mbar_spin(BAR(MB_EMPTY) + 8 * n);
        const int m = n + 5;
        e_tma2d(slot, &mx, BAR(MB_FULL) + 8 * m, (m & 7) * 64, rt * 256 + (m >> 3) * 128);
        slot = slot == sb + OFF_X + 4 * 16384 ? sb + OFF_X : slot + 16384;
        if (n == X2_AT) e_prefetch(P.x + (size_t)(rt * 256 + 128 + hp * 8) * 512, 8192);
        if (n == 7) {
          e_prefetch(P.wo + (size_t)b * 2048, 4096);
          asm volatile("prefetch.tensormap [%0];" ::"l"(&mo) : "memory");
          asm volatile("prefetch.tensormap [%0];" ::"l"(&mout) : "memory");
        }
      }
#pragma unroll 1
      for (int i = 0; i < 8; i++) {
        mbar_wait(BAR(MB_EMPTY + 10) + 8 * ((0x54332222u >> (4 * i)) & 7));
        const int w0 = (0x54736210u >> (4 * i)) & 7;
        e_tma3d(sb + OFF_W + w0 * 16384, &mo, BAR(MB_WO), 0, w0 * 64, (hp & 3) * 2);
      }
    } else {
      if (warp == 15) {
        const uint4 v0 = __ldg((const uint4*)P.wphi + hp * 64 + lane), v1 = __ldg((const uint4*)P.wphi + hp * 64 + 32 + lane);
        sts128(sb + OFF_PHI + (lane & 1) * 256 + (lane >> 1) * 16, v0.x, v0.y, v0.z, v0.w);
        sts128(sb + OFF_PHI + 512 + (lane & 1) * 256 + (lane >> 1) * 16, v1.x, v1.y, v1.z, v1.w);
        const uint32_t one = (((lane >> 3) ^ (lane >> 4)) & 1) ? 0u : ((lane & 1) ? 0x3F800000u : 0x3F80u);
        const int q = (lane >> 1) & 3;
        sts128(sb + OFF_EYE + lane * 16, q == 0 ? one : 0u, q == 1 ? one : 0u, q == 2 ? one : 0u, q == 3 ? one : 0u);
        sts64(sb + OFF_ONE + lane * 8, 0x3F803F80u, 0x3F803F80u);
        asm volatile("fence.proxy.async.shared::cta;" ::: "memory");
        nb_arrive(NB_KREAD, 160);
      }
      uint32_t* cnt = (uint32_t*)(P.xs + X_CNT) + (warp == 13 ? i8 : (warp == 14 ? 8 + rt : 16 + oct)) * 32;
      const unsigned target = (ld_x32(cnt) & ~15u) + 16;
      if (warp != 14) {
        if (warp == 15) mbar_wait(BAR(MB_EMPTY + ZERO_STEP));
        uint4* pz = P.xs + (warp == 13 ? X_PART + (hp * 8 + rt) * 144 : X_Y + b * 1024) + lane;
#pragma unroll 1
        for (int i = (warp == 13 ? 144 : 1024) - lane; i > 0; i -= 32, pz += 32) st_x(pz, 0, 0, 0, 0);
      }
      if (warp == 15) __syncwarp();
      else nb_sync(warp == 13 ? NB_INIT : NB_ODONE, warp == 13 ? 160 : 288);
      if (lane == 0) asm volatile("red.release.gpu.global.add.u32 [%0], %1;" ::"l"(cnt), "r"(warp == 15 ? 2 : 1) : "memory");
      if (lane == 0) TS1(warp == 13 ? 50 : (warp == 14 ? 57 : 53));
      __syncwarp();
      if (warp == 14) nb_arrive(NB_GATE + 1, 160);
      asm volatile("fence.proxy.async.shared::cta;" ::: "memory");
      if (warp == 13) cnt += ((lane & 1 ? b >> 4 : i8 ^ (lane & 4)) - i8) * 32;
#pragma unroll 1
      for (int i = 0; i < SPIN_MAX; i++) {
        unsigned v;
        asm volatile("ld.acquire.gpu.global.u32 %0, [%1];" : "=r"(v) : "l"(cnt) : "memory");
        if (__all_sync(0xffffffffu, (int)(v - target) >= 0)) break;
      }
      if (lane == 0) TS1(warp == 13 ? 51 : (warp == 14 ? 58 : 55));
      if (warp == 15) { nb_arrive(NB_YZ, 160); return; }
      asm volatile("fence.proxy.async.global;" ::: "memory");
      if (warp == 13) {
        mbar_wait(BAR(MB_EMPTY + 11));
        e_expect(BAR(MB_UFULL), 4 * U_CH);
        e_bulk(sb + OFF_U, P.xs + X_UT + b * (U_CH / 4), 4 * U_CH, BAR(MB_UFULL));
      } else {
        const uint4* src = P.xs + X_O + (rt * 4 + (hp >> 2)) * 4096;
        e_bulk(sb + OFF_X + 32768 + 57344, src + 3584, 8192, BAR(MB_O));
        e_bulk(sb + OFF_X + 32768, src, 16384, BAR(MB_O + 1));
        e_bulk(sb + OFF_X + 49152, src + 1024, 16384, BAR(MB_O + 2));
        e_bulk(sb + OFF_STG0, src + 3200, 6144, BAR(MB_O + 3));
        nb_sync(NB_BDONE, 288);
        asm volatile("fence.proxy.async.shared::cta;" ::: "memory");
        e_bulk(sb + OFF_U, src + 2048, 18432, BAR(MB_O + 3));
      }
    }
    return;
  }

  const int t = tid & 127;
  const int g = lane >> 2, c = lane & 3;
  if (wg == 1) {
    mbar_wait(BAR(MB_URAW));
    TS(48);
    uint4* dst = P.xs + X_UT + (i8 * 64 + g) * (U_CH / 16) + (w & 1) * (U_ODD / 16) + U_PAD / 16 + oct * 8 + (w >> 1) * 4 + c;
    const int ln = ((lane >> 1) & 3) + 4 * (lane & 1);
    uint32_t r[8][4];
#pragma unroll
    for (int i = 0; i < 8; i++) ldsm4t(r[i], sb + OFF_STG0 + w * 4096 + ((lane >> 3) * 8 + ln) * 128 + ((i ^ ln) << 4));
#pragma unroll
    for (int i = 0; i < 8; i++) dst[i * (U_CH / 2)] = make_uint4(r[i][0], r[i][1], r[i][2], r[i][3]);
    nb_arrive(NB_INIT, 160);
    if (lane == 0) mbar_arrive(BAR(MB_AUX));
  }
  {
    if (wg == 2) {
      asm volatile("setmaxnreg.inc.sync.aligned.u32 160;");
#pragma unroll
      for (int j = 0; j < 5; j++) { k[j][0] *= ksc; k[j][1] *= ksc; k[j][2] *= ksc; k[j][3] *= ksc; }
#pragma unroll 1
      for (int q = 0; q < 3; q++) {
        const uint32_t src = ((tb + 127) & ~127u) + q * 1536 + lane * 16;
        const uint4 v0 = lds128(src), v1 = lds128(src + 512), v2 = lds128(src + 1024);
        const uint32_t h[10] = {v0.x, v0.y, v0.z, v0.w, v1.x, v1.y, v1.z, v1.w, v2.x, v2.y};
#pragma unroll
        for (int j = 0; j < 10; j++) {
          const float2 f = __half22float2(*(const __half2*)&h[j]);
          k[j >> 1][2 * (j & 1)] = fmaf(f.x, uf(v2.w), k[j >> 1][2 * (j & 1)]);
          k[j >> 1][2 * (j & 1) + 1] = fmaf(f.y, uf(v2.w), k[j >> 1][2 * (j & 1) + 1]);
        }
        k2048 += uf(v2.z);
      }
#pragma unroll
      for (int o2 = 4; o2; o2 >>= 1) k2048 += __shfl_xor_sync(0xffffffffu, k2048, o2);
      if (lane == 0) k[0][0] += bf_lo(dsk);
      __syncwarp();
      TS(34);
      build_tables(tb, lane, k, k2048);
      TS(35);
      uint4* const g_y = P.xs + X_Y;
      conv_channel(sb + OFF_U + w * U_CH, tb, lane, g_y + (size_t)d * 256 + lane);
      nb_arrive(NB_BDONE, 288);
      nb_arrive(NB_Y, 160);
      TS(37);
      if (w == 0) TSDUMP(32);
      return;
    }
    if (wg == 1) {
      mbar_wait(BAR(MB_EMPTY + 4));
      mbar_spin(BAR(MB_EMPTY + 6));
    }
    TS(wg * 16 + 1);
  }

  float acc[2][48];
  {
    uint32_t fb = BAR(MB_FULL) + 64 * wg;
    uint32_t da = (uint32_t)mkdesc(sb + OFF_X, 16, 0, 0) + (wg ? 1024 : 3072), db = (uint32_t)mkdesc(sb + OFF_W, 4096, 0, 0);
    constexpr uint64_t ha = mkdesc(0, 0, 1024, 1), hb = mkdesc(0, 0, 512, 2);
    mbar_spin(fb);
    TS(wg * 16 + 2);
#pragma unroll 1
    for (int kb = 0; kb < 8; kb++) {
      WG_FENCE();
#pragma unroll
      for (int k = 0; k < 4; k++) {
        wgmma_ss_n96(acc[0], ha | (da + 2 * k), hb | (db + 64 * k), k ? 1 : kb);
        wgmma_ss_n96(acc[1], ha | (da + 2 * k + 512), hb | (db + 64 * k), k ? 1 : kb);
      }
      WG_COMMIT();
      if (kb < 7) mbar_spin(fb + 8);
      WG_WAIT(1);
      if (kb > 0) e_arrive(fb + 8 * (MB_EMPTY - MB_FULL - 1));
      fb += 8; db += 768;
      da = da == (uint32_t)mkdesc(sb + OFF_X + 65536, 16, 0, 0) ? da - 4096 : da + 1024;
    }
    if (wg == 0) nb_sync(NB_KREAD, 160);
    asm volatile("setmaxnreg.inc.sync.aligned.u32 160;");
    WG_WAIT(0);
    e_arrive(fb + 8 * (MB_EMPTY - MB_FULL - 1));
    SPLIT();
  }
  TS(wg * 16 + 3);

  constexpr uint32_t stg0 = sb + OFF_STG0, stg1 = sb + OFF_X + 32768;
  uint4* const g_part = P.xs + X_PART;
  uint4* const g_o = P.xs + X_O;
  constexpr uint32_t kvs = stg0;
  auto pack8 = [](const float* a) { return make_uint4(pack_bf(a[0], a[1]), pack_bf(a[2], a[3]), pack_bf(a[4], a[5]), pack_bf(a[6], a[7])); };
  auto feat = [&](const uint4 (&af)[4], float (&p)[4][8]) {
    WG_FENCE();
#pragma unroll
    for (int u = 0; u < 4; u++) wgmma_rs_n16(p[u], af[u], qdesc(sb + OFF_PHI + (u & 1) * 512), 0);
    WG_COMMIT();
  };
  auto packp = [](const float (&p)[4][8], uint32_t (&pw)[16]) {
#pragma unroll
    for (int i = 0; i < 16; i++) pw[i] = pack_bf(p[i >> 2][(i & 1) + 2 * (i & 2)], p[i >> 2][(i & 1) + 2 * (i & 2) + 2]);
  };
  auto contract = [&](float (&kc)[20], uint32_t stg, int acc_in) {
    WG_FENCE();
#pragma unroll
    for (int s = 0; s < 8; s++) wgmma_ss_n40(kc, qdesc(stg + s * SLAB), qdesc(stg + s * SLAB + 2048), s ? 1 : acc_in);
    WG_COMMIT();
    WG_WAIT(0);
  };
  uint32_t eq[32];
  {
    uint4 af[4], aq[4], vp[4];
    float p[4][8];
#pragma unroll
    for (int u = 0; u < 4; u++) af[u] = pack8(acc[u >> 1] + 16 + 8 * (u & 1));
    feat(af, p);
#pragma unroll
    for (int u = 0; u < 4; u++) { aq[u] = pack8(acc[u >> 1] + 8 * (u & 1)); vp[u] = pack8(acc[u >> 1] + 32 + 8 * (u & 1)); }
    WG_WAIT(0);
    uint32_t pw[16], ek[32];
    packp(p, pw);
#pragma unroll
    for (int u = 0; u < 4; u++) dual_exp(pw + 4 * u, ek + 8 * u);
    TS(wg * 16 + 12);
    if (wg && (ek[0] & ek[8] & ek[16] & ek[31]) != 0xffffffffu) nb_arrive(NB_GATE, 256);
    mbar_spin(wg ? BAR(MB_EMPTY + 15) : BAR(MB_AUX));
    float rs[8][4];
    WG_FENCE();
#pragma unroll
    for (int i = 0; i < 8; i++) wgmma_rs_n8(rs[i], make_uint4(ek[4 * i], ek[4 * i + 1], ek[4 * i + 2], ek[4 * i + 3]), qdesc(sb + OFF_ONE), 0);
    WG_COMMIT();
    feat(aq, p);
    const uint32_t sl = (wg ? stg1 : stg0) + w * SLAB + lane * 16;
#pragma unroll
    for (int i = 0; i < 4; i++) stsm4(sl + (i >> 1) * 4 * SLAB + 2048 + (i & 1) * 512, vp[i].x, vp[i].y, vp[i].z, vp[i].w);
    sts128(sl + (lane >> 4) * (4 * SLAB - 256) + 3072, 0x3F803F80u, 0x3F803F80u, 0x3F803F80u, 0x3F803F80u);
    WG_WAIT(1);
#pragma unroll
    for (int i = 0; i < 8; i++) {
      normalise(ek + 4 * i, rs[i]);
      stsm4(sl + (i >> 2) * 4 * SLAB + (i & 3) * 512, ek[4 * i], ek[4 * i + 1], ek[4 * i + 2], ek[4 * i + 3]);
    }
    asm volatile("fence.proxy.async.shared::cta;" ::: "memory");
    TS(wg * 16 + 13);
    if (wg) {
      nb_arrive(NB_ST0, 256);
    } else {
      float kc[20];
      uint4* pp = g_part + (size_t)(hp * 8 + rt) * 144 + t;
      uint32_t* pz = (uint32_t*)(pp - t + 128) + w * 16 + c * 8 + g;
      asm volatile("" : "+l"(pp), "+l"(pz));
      nb_sync(NB_WG0, 128);
      contract(kc, stg0, 0);
      mbar_wait(BAR(MB_UFULL));
      TS(15);
      nb_sync(NB_ST0, 256);
      contract(kc, stg1, 1);
      TS(6);
      float kv[8];
#pragma unroll
      for (int i = 0; i < 8; i++) kv[i] = w & 2 ? kc[8 + i] : kc[i];
      st_x(pp, nz(pack_bf(kv[0], kv[1])), pack_bf(kv[2], kv[3]), pack_bf(kv[4], kv[5]), pack_bf(kv[6], kv[7]));
      if (c < 2) st_x32(pz, nz(fu(c ? kc[18] : kc[16])));
      TS(5);
    }
    SPLIT();
    WG_WAIT(0);
    packp(p, pw);
#pragma unroll
    for (int u = 0; u < 4; u++) dual_exp(pw + 4 * u, eq + 8 * u);
    SPLIT();
  }
  TS(wg * 16 + 4);
  if (wg == 1) {
    mbar_wait(BAR(MB_UFULL));
    const uint4* ps = g_part + (size_t)hp * 8 * 144 + t;
    const uint32_t* zs = (const uint32_t*)(g_part + (size_t)(hp * 8 + (lane >> 4) * 4) * 144 + 128) + w * 16 + (lane & 15);
    uint4 v[8];
    uint32_t zv[4];
#pragma unroll 1
    for (int it = 0; it < SPIN_MAX; it++) {
#pragma unroll
      for (int i = 0; i < 8; i++) v[i] = ld_x(ps + i * 144);
#pragma unroll
      for (int i = 0; i < 4; i++) zv[i] = ld_x32(zs + i * 576);
      uint32_t m = min(min(zv[0], zv[1]), min(zv[2], zv[3]));
#pragma unroll
      for (int i = 0; i < 8; i++) m = min(m, v[i].x);
      if (__all_sync(0xffffffffu, m != 0)) break;
    }
    float s[8];
    float s2[8];
#pragma unroll
    for (int i = 0; i < 8; i++) s[i] = s2[i] = 0.f;
    const uint32_t eye = (g >> 1) == c ? ((g & 1) ? 0x3F800000u : 0x3F80u) : 0u;
#pragma unroll
    for (int r = 0; r < 8; r++) {
      mma_k8((r & 1) ? s2 : s, v[r].x, v[r].y, eye);
      mma_k8(((r & 1) ? s2 : s) + 4, v[r].z, v[r].w, eye);
    }
#pragma unroll
    for (int i = 0; i < 8; i++) s[i] += s2[i];
    float zsum = (uf(zv[0]) + uf(zv[1])) + (uf(zv[2]) + uf(zv[3]));
    zsum += __shfl_xor_sync(0xffffffffu, zsum, 16);
    const uint32_t z1 = pack_bf(zsum, 1.f);
    if (lane < 16) sts128(kvs + w * 768 + 512 + lane * 16, z1, z1, z1, z1);
    stsm4(kvs + w * 768 + lane * 16, pack_bf(s[0], s[1]), pack_bf(s[2], s[3]), pack_bf(s[4], s[5]), pack_bf(s[6], s[7]));
    TS(22);
  }
  nb_sync(NB_KV, 256);
  {
    float n[8][12];
    uint32_t kf[6][4];
#pragma unroll
    for (int i = 0; i < 6; i++) ldsm4t(kf[i], kvs + i * 512 + lane * 16);
#pragma unroll
    for (int i = 0; i < 8; i++)
#pragma unroll
      for (int j = 2; j >= 0; j--) {
        const int blk = (i & 3) * 6 + 2 * j;
        mma0(n[i][4 * j], n[i][4 * j + 1], n[i][4 * j + 2], n[i][4 * j + 3], eq[4 * i], eq[4 * i + 1], eq[4 * i + 2], eq[4 * i + 3],
             kf[blk >> 2][blk & 3], kf[blk >> 2][(blk & 3) + 1]);
      }
    uint32_t* od = (uint32_t*)(g_o + (size_t)((rt * 4 + wg * 2) * 32 + hp * 2) * 128) + w * 64 + lane;
#pragma unroll
    for (int u = 0; u < 4; u++) {
      float(&np)[12] = n[2 * u];
      const float(&nm)[12] = n[2 * u + 1];
      const float q0 = np[9] * rcp(nm[9]), q1 = np[11] * rcp(nm[11]);
      const float r0 = rcp(fmaf(nm[8], q0, fmaf(np[9], 1e-6f, np[8]))), r1 = rcp(fmaf(nm[10], q1, fmaf(np[11], 1e-6f, np[10])));
#pragma unroll
      for (int i = 0; i < 8; i++) np[i] = fmaf(nm[i], (i & 2) ? q1 : q0, np[i]);
      uint32_t* o = od + (u >> 1) * 16384 + (u & 1) * 512;
      o[0] = pack_bf(np[0] * r0, np[1] * r0);
      o[32] = pack_bf(np[2] * r1, np[3] * r1);
      o[256] = pack_bf(np[4] * r0, np[5] * r0);
      o[288] = pack_bf(np[6] * r1, np[7] * r1);
      if (u == 1) SPLIT();
    }
  }
  TS(wg * 16 + 7);
  nb_arrive(NB_ODONE, 288);
  if (wg) {
    const uint4* src = P.xs + X_Y + (oct * 32 + c * 8) * 256 + (2 * w + (g >> 2)) * 32 + i8 * 4 + (g & 3);
    __nv_bfloat16* dst = P.out + (size_t)((2 * w + (g >> 2)) * 256 + i8 * 16 + (g & 3) * 2) * 1024 + 512 + oct * 32 + c * 8;
    nb_sync(NB_GATE + 1, 160);
    nb_sync(NB_Y + w, 160);
    uint4 v[8];
#pragma unroll 1
    for (int it = 0; it < SPIN_MAX; it++) {
      uint32_t m = 0xffffffffu;
#pragma unroll
      for (int i = 0; i < 8; i++) v[i] = ld_x(src + i * 256);
#pragma unroll
      for (int i = 0; i < 8; i++) m = min(m, v[i].x);
      if (__all_sync(0xffffffffu, m != 0)) break;
    }
#pragma unroll
    for (int i = 0; i < 8; i++) *(uint4*)(dst + (size_t)((i >> 2) * 128 + ((i >> 1) & 1) * 8 + (i & 1)) * 1024) = tr_row(v, i);
    TS(31);
    GT(63);
    if (w == 0) TSDUMP(16);
    return;
  }
  mbar_wait(BAR(MB_WO));
  nb_sync(NB_BDONE, 288);
  TS(8);
  mbar_spin(BAR(MB_O));
  TS(9);
  constexpr uint64_t ha = mkdesc(0, 0, 128, 0), hb = mkdesc(0, 0, 1024, 1);
  constexpr uint32_t da0 = (uint32_t)mkdesc(stg1, 1024, 0, 0), db0 = (uint32_t)mkdesc(sb + OFF_W, 8192, 0, 0);
  const uint32_t ot = ((sb + OFF_T + 1023) & ~1023u) + w * 4096;
  auto store_half = [&](const float* oc, int hf) {
#pragma unroll
    for (int i = 0; i < 8; i += 2)
      stsm4(ot + hf * 2048 + (lane & 15) * 128 + (((i + (lane >> 4)) ^ lane) & 7) * 16, pack_bf(oc[4 * i], oc[4 * i + 1]),
            pack_bf(oc[4 * i + 2], oc[4 * i + 3]), pack_bf(oc[4 * i + 4], oc[4 * i + 5]), pack_bf(oc[4 * i + 6], oc[4 * i + 7]));
    asm volatile("fence.proxy.async.shared::cta;" ::: "memory");
    __syncwarp();
    e_store2d(&mout, ot + hf * 2048, (hp & 3) * 128 + hf * 64, (rt * 4 + (hp >> 2)) * 64 + w * 16);
  };
  float oc[64];
#pragma unroll 1
  for (int j = 0; j < 8; j++) {
    const int kb = (j + 7) & 7;
    if ((j & 1) && j < 6) mbar_spin(BAR(MB_O + 1) + 4 * (j - 1));
    WG_FENCE();
#pragma unroll
    for (int k = 0; k < 4; k++) wgmma_ss_n128(oc, ha | (da0 + 512 * kb + 128 * k), hb | (db0 + 1024 * kb + 128 * k), k ? 1 : j);
    WG_COMMIT();
  }
  WG_WAIT(0);
  TS(10);
  store_half(oc, 0);
  store_half(oc + 32, 1);
  asm volatile(ELECT "cp.async.bulk.commit_group;\n@p cp.async.bulk.wait_group.read 0;\n}\n" ::: "memory");
  TS(wg * 16 + 11);
  GT(61 + wg);
  if (w == 0) TSDUMP(0);
  if (w == 1) TSDUMP(48);
}

typedef CUresult (*EncodeFn)(CUtensorMap*, CUtensorMapDataType, cuuint32_t, void*, const cuuint64_t*, const cuuint64_t*,
                             const cuuint32_t*, const cuuint32_t*, CUtensorMapInterleave, CUtensorMapSwizzle,
                             CUtensorMapL2promotion, CUtensorMapFloatOOBfill);

}

extern "C" void kernel_launch(void* const* d_in, const int* in_sizes, int n_in, void* d_out, int out_size) {
  (void)in_sizes; (void)n_in; (void)out_size;
  void* fn = nullptr;
  cudaDriverEntryPointQueryResult qr;
  cudaGetDriverEntryPoint("cuTensorMapEncodeTiled", &fn, cudaEnableDefault, &qr);
  EncodeFn enc = (EncodeFn)fn;
  CUtensorMap mx, mw, mo, mu, mout, mw4;
  const cuuint32_t es[5] = {1, 1, 1, 1, 1};
  {
    cuuint64_t dims[2] = {512, 2048}, st[1] = {1024};
    cuuint32_t box[2] = {64, 128};
    enc(&mx, CU_TENSOR_MAP_DATA_TYPE_BFLOAT16, 2, d_in[0], dims, st, box, es, CU_TENSOR_MAP_INTERLEAVE_NONE,
        CU_TENSOR_MAP_SWIZZLE_128B, CU_TENSOR_MAP_L2_PROMOTION_L2_128B, CU_TENSOR_MAP_FLOAT_OOB_FILL_NONE);
  }
  {
    cuuint64_t dims[3] = {512, 512, 3}, st[2] = {3072, 1024};
    cuuint32_t box[3] = {32, 64, 3};
    enc(&mw, CU_TENSOR_MAP_DATA_TYPE_BFLOAT16, 3, d_in[1], dims, st, box, es, CU_TENSOR_MAP_INTERLEAVE_NONE,
        CU_TENSOR_MAP_SWIZZLE_64B, CU_TENSOR_MAP_L2_PROMOTION_L2_128B, CU_TENSOR_MAP_FLOAT_OOB_FILL_NONE);
  }
  {
    cuuint64_t dims[3] = {64, 512, 8}, st[2] = {1024, 128};
    cuuint32_t box[3] = {64, 64, 2};
    enc(&mo, CU_TENSOR_MAP_DATA_TYPE_BFLOAT16, 3, d_in[3], dims, st, box, es, CU_TENSOR_MAP_INTERLEAVE_NONE,
        CU_TENSOR_MAP_SWIZZLE_128B, CU_TENSOR_MAP_L2_PROMOTION_L2_128B, CU_TENSOR_MAP_FLOAT_OOB_FILL_NONE);
  }
  {
    cuuint64_t dims[4] = {512, 4, 16, 32}, st[3] = {16384, 1024, 65536};
    cuuint32_t box[4] = {64, 4, 16, 2};
    enc(&mu, CU_TENSOR_MAP_DATA_TYPE_BFLOAT16, 4, d_in[4], dims, st, box, es, CU_TENSOR_MAP_INTERLEAVE_NONE,
        CU_TENSOR_MAP_SWIZZLE_128B, CU_TENSOR_MAP_L2_PROMOTION_L2_128B, CU_TENSOR_MAP_FLOAT_OOB_FILL_NONE);
  }
  {
    cuuint64_t dims[2] = {1024, 2048}, st[1] = {2048};
    cuuint32_t box[2] = {64, 16};
    enc(&mout, CU_TENSOR_MAP_DATA_TYPE_BFLOAT16, 2, d_out, dims, st, box, es, CU_TENSOR_MAP_INTERLEAVE_NONE,
        CU_TENSOR_MAP_SWIZZLE_128B, CU_TENSOR_MAP_L2_PROMOTION_NONE, CU_TENSOR_MAP_FLOAT_OOB_FILL_NONE);
  }
  {
    cuuint64_t dims[4] = {512, 64, 3, 8}, st[3] = {3072, 1024, 64 * 3072};
    cuuint32_t box[4] = {32, 64, 3, 2};
    enc(&mw4, CU_TENSOR_MAP_DATA_TYPE_BFLOAT16, 4, d_in[1], dims, st, box, es, CU_TENSOR_MAP_INTERLEAVE_NONE,
        CU_TENSOR_MAP_SWIZZLE_64B, CU_TENSOR_MAP_L2_PROMOTION_L2_128B, CU_TENSOR_MAP_FLOAT_OOB_FILL_NONE);
  }
  Params P;
  P.x = (const __nv_bfloat16*)d_in[0];
  P.wphi = (const __nv_bfloat16*)d_in[2];
  P.wo = (const __nv_bfloat16*)d_in[3];
  P.logA = (const __nv_bfloat16*)d_in[5];
  P.Aim = (const __nv_bfloat16*)d_in[6];
  P.Cre = (const __nv_bfloat16*)d_in[7];
  P.Cim = (const __nv_bfloat16*)d_in[8];
  P.logdt = (const __nv_bfloat16*)d_in[9];
  P.Dskip = (const __nv_bfloat16*)d_in[10];
  P.out = (__nv_bfloat16*)d_out;
  cudaGetSymbolAddress((void**)&P.xs, g_x);
  P.ts = nullptr;
  cudaFuncSetAttribute(fused_kernel, cudaFuncAttributeMaxDynamicSharedMemorySize, SMEM_BYTES);
  fused_kernel<<<NCTA, NTHREADS, SMEM_BYTES>>>(P, mx, mw, mo, mu, mout, mw4);
}
```

```cpp
#include <cuda_runtime.h>
#include <cuda_bf16.h>
#include <cuda_fp16.h>
#include <cuda.h>
#include <stdint.h>

#define DBG_TS 0

namespace {

constexpr int NTHREADS = 512;
constexpr int NCTA = 128;
constexpr int OFF_W = 0;
constexpr int OFF_X = 98304;
constexpr int OFF_U = OFF_X + 65536;
constexpr int U_CH = 4416, U_ODD = 2240, U_PAD = 128;
constexpr int OFF_STG0 = OFF_U + 18432;
constexpr int SLAB = 3328;
constexpr int OFF_T = OFF_STG0 + 8 * SLAB;
constexpr int T_CH = 5216;
constexpr int T_D = 0;
constexpr int T_5 = 2144;
constexpr int T_3 = T_5 + 384;
constexpr int T_7 = T_5 + 1024;
constexpr int T_9 = T_7 + 320;
constexpr int T_KC = T_9 + 320;
constexpr int T_ST = T_5 - 1024;
constexpr int OFF_PHI = OFF_T + 4 * T_CH;
constexpr int OFF_EYE = OFF_PHI + 1024, OFF_ONE = OFF_EYE + 512;
constexpr int OFF_BAR = OFF_ONE + 256;
constexpr int SMEM_BYTES = OFF_BAR + 512 + 256 * DBG_TS;
constexpr uint32_t SB = 1024;
static_assert(T_KC + 2 * 656 <= T_CH, "table size");
static_assert(SMEM_BYTES <= 232448, "smem");
constexpr int MB_URAW = 0, MB_FULL = 1  , MB_WO = 17, MB_UFULL = 18, MB_O = 19  ,
              MB_EMPTY = 23  , MB_AUX = 39;
__host__ __device__ constexpr uint32_t BAR(int i) { return SB + OFF_BAR + 8 * i; }
constexpr int NB_WG0 = 1, NB_ODONE = 2, NB_ST0 = 3  , NB_KV = 5, NB_YZ = 6, NB_INIT = 7, NB_PREP = 8, NB_PROD = 9, NB_KREAD = 10, NB_BDONE = 11, NB_GATE = 12,
              NB_Y = 7  ;
#define X2_AT -1
#define GATE_B 1
#define POLL 0
#define U_AT 2
#define ZERO_STEP 12
constexpr int SPIN_MAX = 1 << 16;

constexpr int X_CNT = 0;
constexpr int X_PART = 256;
constexpr int X_O = X_PART + 16 * 8 * 144;
constexpr int X_Y = X_O + 32 * 32 * 128;
constexpr int X_UT = X_Y + 512 * 8 * 32;
constexpr int X_SIZE = X_UT + 512 * (U_CH / 16);
__device__ __align__(128) uint4 g_x[X_SIZE];
extern __shared__ uint8_t smem_raw[];
#define TS(i) do {} while (0)
#define TS1(i) do {} while (0)
#define GT(i) do {} while (0)
#define TSDUMP(base) do {} while (0)

__device__ __forceinline__ uint32_t smem_u32(const void* p) { return (uint32_t)__cvta_generic_to_shared(p); }
__device__ __forceinline__ void mbar_arrive(uint32_t b) {
  asm volatile("mbarrier.arrive.shared::cta.b64 _, [%0];" ::"r"(b) : "memory");
}
__device__ __forceinline__ void mbar_wait(uint32_t b) {
  uint32_t done = 0;
#pragma unroll 1
  for (int i = 0; i < SPIN_MAX && !done; i++) {
    asm volatile("{\n.reg .pred p;\nmbarrier.try_wait.parity.shared::cta.b64 p, [%1], 0, 4000;\nselp.u32 %0, 1, 0, p;\n}\n"
                 : "=r"(done) : "r"(b) : "memory");
  }
}
__device__ __forceinline__ void mbar_spin(uint32_t b) {
  uint32_t done = 0;
#pragma unroll 1
  for (int i = 0; i < (SPIN_MAX << 4) && !done; i++) {
    asm volatile("{\n.reg .pred p;\nmbarrier.try_wait.parity.shared::cta.b64 p, [%1], 0;\nselp.u32 %0, 1, 0, p;\n}\n"
                 : "=r"(done) : "r"(b) : "memory");
  }
}
__device__ __forceinline__ void mbar_init(uint32_t b, int n) {
  asm volatile("mbarrier.init.shared::cta.b64 [%0], %1;" ::"r"(b), "r"(n) : "memory");
}
__device__ __forceinline__ void mbar_expect(uint32_t b, int bytes) {
  asm volatile("mbarrier.arrive.expect_tx.shared::cta.b64 _, [%0], %1;" ::"r"(b), "r"(bytes) : "memory");
}
__device__ __forceinline__ void nb_sync(int id, int n) { asm volatile("bar.sync %0, %1;" ::"r"(id), "r"(n) : "memory"); }
__device__ __forceinline__ void nb_arrive(int id, int n) { asm volatile("bar.arrive %0, %1;" ::"r"(id), "r"(n) : "memory"); }
#define ELECT "{\n.reg .pred p;\nelect.sync _|p, 0xffffffff;\n@p "
__device__ __forceinline__ void e_arrive(uint32_t b) {
  asm volatile(ELECT "mbarrier.arrive.shared::cta.b64 _, [%0];\n}\n" ::"r"(b) : "memory");
}
__device__ __forceinline__ void e_expect(uint32_t b, int bytes) {
  asm volatile(ELECT "mbarrier.arrive.expect_tx.shared::cta.b64 _, [%0], %1;\n}\n" ::"r"(b), "r"(bytes) : "memory");
}
__device__ __forceinline__ void e_tma2d(uint32_t dst, const CUtensorMap* m, uint32_t bar, int c0, int c1) {
  asm volatile(ELECT "cp.async.bulk.tensor.2d.shared::cluster.global.mbarrier::complete_tx::bytes [%0], [%1, {%3,%4}], [%2];\n}\n"
               ::"r"(dst), "l"(m), "r"(bar), "r"(c0), "r"(c1) : "memory");
}
__device__ __forceinline__ void e_tma3d(uint32_t dst, const CUtensorMap* m, uint32_t bar, int c0, int c1, int c2) {
  asm volatile(ELECT "cp.async.bulk.tensor.3d.shared::cluster.global.mbarrier::complete_tx::bytes [%0], [%1, {%3,%4,%5}], [%2];\n}\n"
               ::"r"(dst), "l"(m), "r"(bar), "r"(c0), "r"(c1), "r"(c2) : "memory");
}
__device__ __forceinline__ void e_tma4d(uint32_t dst, const CUtensorMap* m, uint32_t bar, int c0, int c3) {
  asm volatile(ELECT "cp.async.bulk.tensor.4d.shared::cluster.global.mbarrier::complete_tx::bytes [%0], [%1, {%3,%5,%5,%4}], [%2];\n}\n"
               ::"r"(dst), "l"(m), "r"(bar), "r"(c0), "r"(c3), "r"(0) : "memory");
}
__device__ __forceinline__ void e_bulk(uint32_t dst, const void* src, int bytes, uint32_t bar) {
  asm volatile(ELECT "cp.async.bulk.shared::cluster.global.mbarrier::complete_tx::bytes [%0], [%1], %2, [%3];\n}\n"
               ::"r"(dst), "l"(src), "r"(bytes), "r"(bar) : "memory");
}
__device__ __forceinline__ void e_prefetch(const void* p, int bytes) {
  asm volatile(ELECT "cp.async.bulk.prefetch.L2.global [%0], %1;\n}\n" ::"l"(p), "r"(bytes) : "memory");
}
__device__ __forceinline__ void e_store2d(const CUtensorMap* m, uint32_t src, int c0, int c1) {
  asm volatile(ELECT "cp.async.bulk.tensor.2d.global.shared::cta.bulk_group [%0, {%2,%3}], [%1];\n}\n"
               ::"l"(m), "r"(src), "r"(c0), "r"(c1) : "memory");
}
__host__ __device__ constexpr uint64_t mkdesc(uint32_t addr, uint32_t lbo, uint32_t sbo, int swz) {
  return (uint64_t)((addr & 0x3FFFF) >> 4) | ((uint64_t)(lbo >> 4) << 16) | ((uint64_t)(sbo >> 4) << 32) |
         ((uint64_t)swz << 62);
}
#define SPLIT() asm volatile("{\n.reg .pred p;\nsetp.eq.u32 p, %0, %1;\n@p exit;\n}\n" ::"r"(blockIdx.y), "n"(__LINE__) : "memory")
#define SPLITN(n) asm volatile("{\n.reg .pred p;\nsetp.eq.u32 p, %0, %1;\n@p exit;\n}\n" ::"r"(blockIdx.y), "r"(4096 + (n)) : "memory")
#define WG_FENCE() asm volatile("wgmma.fence.sync.aligned;" ::: "memory")
#define WG_COMMIT() asm volatile("wgmma.commit_group.sync.aligned;" ::: "memory")
#define WG_WAIT(n) asm volatile("wgmma.wait_group.sync.aligned " #n ";" ::: "memory")

__device__ __forceinline__ void mma(float& d0, float& d1, float& d2, float& d3, uint32_t a0, uint32_t a1, uint32_t a2,
                                    uint32_t a3, uint32_t b0, uint32_t b1) {
  asm volatile("mma.sync.aligned.m16n8k16.row.col.f32.bf16.bf16.f32 {%0,%1,%2,%3},{%4,%5,%6,%7},{%8,%9},{%0,%1,%2,%3};"
               : "+f"(d0), "+f"(d1), "+f"(d2), "+f"(d3)
               : "r"(a0), "r"(a1), "r"(a2), "r"(a3), "r"(b0), "r"(b1));
}
__device__ __forceinline__ void mmac(float (&d)[4], uint32_t a0, uint32_t a1, uint32_t a2, uint32_t a3, uint32_t b0,
                                     uint32_t b1, const float (&c)[4]) {
  asm volatile("mma.sync.aligned.m16n8k16.row.col.f32.bf16.bf16.f32 {%0,%1,%2,%3},{%4,%5,%6,%7},{%8,%9},{%10,%11,%12,%13};"
               : "=f"(d[0]), "=f"(d[1]), "=f"(d[2]), "=f"(d[3])
               : "r"(a0), "r"(a1), "r"(a2), "r"(a3), "r"(b0), "r"(b1), "f"(c[0]), "f"(c[1]), "f"(c[2]), "f"(c[3]));
}
__device__ __forceinline__ void mma_p(int p, float (&d)[4], uint32_t a0, uint32_t a1, uint32_t a2, uint32_t a3, uint32_t b0, uint32_t b1) {
  asm volatile("{\n.reg .pred q;\nsetp.ne.b32 q, %10, 0;\n"
               "@q mma.sync.aligned.m16n8k16.row.col.f32.bf16.bf16.f32 {%0,%1,%2,%3},{%4,%5,%6,%7},{%8,%9},{%0,%1,%2,%3};\n}\n"
               : "+f"(d[0]), "+f"(d[1]), "+f"(d[2]), "+f"(d[3])
               : "r"(a0), "r"(a1), "r"(a2), "r"(a3), "r"(b0), "r"(b1), "r"(p));
}
__device__ __forceinline__ void mmac_p(int p, float (&d)[4], uint32_t a0, uint32_t a1, uint32_t a2, uint32_t a3, uint32_t b0,
                                       uint32_t b1, const float (&c)[4]) {
  asm volatile("{\n.reg .pred q;\nsetp.ne.b32 q, %14, 0;\n"
               "@q mma.sync.aligned.m16n8k16.row.col.f32.bf16.bf16.f32 {%0,%1,%2,%3},{%4,%5,%6,%7},{%8,%9},{%10,%11,%12,%13};\n}\n"
               : "+f"(d[0]), "+f"(d[1]), "+f"(d[2]), "+f"(d[3])
               : "r"(a0), "r"(a1), "r"(a2), "r"(a3), "r"(b0), "r"(b1), "f"(c[0]), "f"(c[1]), "f"(c[2]), "f"(c[3]), "r"(p));
}
__device__ __forceinline__ void mma_h(float (&d)[4], const uint32_t (&a)[4], uint32_t b0, uint32_t b1) {
  asm volatile("mma.sync.aligned.m16n8k16.row.col.f32.f16.f16.f32 {%0,%1,%2,%3},{%4,%5,%6,%7},{%8,%9},{%0,%1,%2,%3};"
               : "+f"(d[0]), "+f"(d[1]), "+f"(d[2]), "+f"(d[3]) : "r"(a[0]), "r"(a[1]), "r"(a[2]), "r"(a[3]), "r"(b0), "r"(b1));
}
__device__ __forceinline__ void mma0(float& d0, float& d1, float& d2, float& d3, uint32_t a0, uint32_t a1, uint32_t a2,
                                     uint32_t a3, uint32_t b0, uint32_t b1) {
  asm volatile("mma.sync.aligned.m16n8k16.row.col.f32.bf16.bf16.f32 {%0,%1,%2,%3},{%4,%5,%6,%7},{%8,%9},{%10,%10,%10,%10};"
               : "=f"(d0), "=f"(d1), "=f"(d2), "=f"(d3)
               : "r"(a0), "r"(a1), "r"(a2), "r"(a3), "r"(b0), "r"(b1), "f"(0.f));
}
__device__ __forceinline__ uint32_t pack_bf(float lo, float hi) {
  uint32_t r;
  asm("cvt.rn.bf16x2.f32 %0, %1, %2;" : "=r"(r) : "f"(hi), "f"(lo));
  return r;
}
__device__ __forceinline__ float bf_lo(uint32_t w) { return __uint_as_float(w << 16); }
__device__ __forceinline__ float bf_hi(uint32_t w) { return __uint_as_float(w & 0xffff0000u); }
__device__ __forceinline__ float bf_round(float x) { return __bfloat162float(__float2bfloat16_rn(x)); }
__device__ __forceinline__ uint32_t bmax2(uint32_t a, uint32_t b) {
  uint32_t r; asm("max.bf16x2 %0, %1, %2;" : "=r"(r) : "r"(a), "r"(b)); return r;
}
__device__ __forceinline__ uint32_t bmin2(uint32_t a, uint32_t b) {
  uint32_t r; asm("min.bf16x2 %0, %1, %2;" : "=r"(r) : "r"(a), "r"(b)); return r;
}
__device__ __forceinline__ float ex2(float x) { float r; asm("ex2.approx.ftz.f32 %0, %1;" : "=f"(r) : "f"(x)); return r; }
__device__ __forceinline__ float rcp(float x) { float r; asm("rcp.approx.ftz.f32 %0, %1;" : "=f"(r) : "f"(x)); return r; }
__device__ __forceinline__ void ldsm4(uint32_t (&r)[4], uint32_t a) {
  asm volatile("ldmatrix.sync.aligned.m8n8.x4.shared.b16 {%0,%1,%2,%3}, [%4];"
               : "=r"(r[0]), "=r"(r[1]), "=r"(r[2]), "=r"(r[3]) : "r"(a) : "memory");
}
__device__ __forceinline__ void ldsm4t(uint32_t (&r)[4], uint32_t a) {
  asm volatile("ldmatrix.sync.aligned.m8n8.x4.trans.shared.b16 {%0,%1,%2,%3}, [%4];"
               : "=r"(r[0]), "=r"(r[1]), "=r"(r[2]), "=r"(r[3]) : "r"(a) : "memory");
}
__device__ __forceinline__ void stsm4(uint32_t a, uint32_t r0, uint32_t r1, uint32_t r2, uint32_t r3) {
  asm volatile("stmatrix.sync.aligned.m8n8.x4.shared.b16 [%0], {%1,%2,%3,%4};"
               ::"r"(a), "r"(r0), "r"(r1), "r"(r2), "r"(r3) : "memory");
}
__device__ __forceinline__ uint32_t lds32(uint32_t a) {
  uint32_t r; asm volatile("ld.shared.u32 %0, [%1];" : "=r"(r) : "r"(a) : "memory"); return r;
}
__device__ __forceinline__ uint32_t lds16(uint32_t a) {
  uint32_t r; asm volatile("{\n.reg .u16 h;\nld.shared.u16 h, [%1];\ncvt.u32.u16 %0, h;\n}\n" : "=r"(r) : "r"(a) : "memory"); return r;
}
__device__ __forceinline__ uint2 lds64(uint32_t a) {
  uint2 r; asm volatile("ld.shared.v2.u32 {%0,%1}, [%2];" : "=r"(r.x), "=r"(r.y) : "r"(a) : "memory"); return r;
}
__device__ __forceinline__ uint4 lds128(uint32_t a) {
  uint4 r;
  asm volatile("ld.shared.v4.u32 {%0,%1,%2,%3}, [%4];" : "=r"(r.x), "=r"(r.y), "=r"(r.z), "=r"(r.w) : "r"(a) : "memory");
  return r;
}
__device__ __forceinline__ void sts32(uint32_t a, uint32_t v) { asm volatile("st.shared.u32 [%0], %1;" ::"r"(a), "r"(v) : "memory"); }
__device__ __forceinline__ void sts16(uint32_t a, uint32_t v) {
  asm volatile("{\n.reg .u16 h;\ncvt.u16.u32 h, %1;\nst.shared.u16 [%0], h;\n}\n" ::"r"(a), "r"(v) : "memory");
}
__device__ __forceinline__ void sts64(uint32_t a, uint32_t x, uint32_t y) {
  asm volatile("st.shared.v2.u32 [%0], {%1,%2};" ::"r"(a), "r"(x), "r"(y) : "memory");
}
__device__ __forceinline__ void sts128(uint32_t a, uint32_t x, uint32_t y, uint32_t z, uint32_t w) {
  asm volatile("st.shared.v4.u32 [%0], {%1,%2,%3,%4};" ::"r"(a), "r"(x), "r"(y), "r"(z), "r"(w) : "memory");
}
__device__ __forceinline__ uint4 ld_x(const uint4* p) {
  uint4 r;
  asm volatile("{\n.reg .b128 t;\nld.relaxed.gpu.global.b128 t, [%4];\nmov.b128 {%0,%1,%2,%3}, t;\n}\n"
               : "=r"(r.x), "=r"(r.y), "=r"(r.z), "=r"(r.w) : "l"(p) : "memory");
  return r;
}
__device__ __forceinline__ uint32_t ld_x32(const uint32_t* p) {
  uint32_t r; asm volatile("ld.relaxed.gpu.global.u32 %0, [%1];" : "=r"(r) : "l"(p) : "memory"); return r;
}
__device__ __forceinline__ void st_x(uint4* p, uint32_t x, uint32_t y, uint32_t z, uint32_t w) {
  asm volatile("{\n.reg .b128 t;\nmov.b128 t, {%1,%2,%3,%4};\nst.relaxed.gpu.global.b128 [%0], t;\n}\n"
               ::"l"(p), "r"(x), "r"(y), "r"(z), "r"(w) : "memory");
}
__device__ __forceinline__ void st_x_p(int p, uint4* a, uint32_t x, uint32_t y, uint32_t z, uint32_t w) {
  asm volatile("{\n.reg .b128 t;\n.reg .pred q;\nsetp.ne.b32 q, %5, 0;\nmov.b128 t, {%1,%2,%3,%4};\n@q st.relaxed.gpu.global.b128 [%0], t;\n}\n"
               ::"l"(a), "r"(x), "r"(y), "r"(z), "r"(w), "r"(p) : "memory");
}
__device__ __forceinline__ void sts64_p(int p, uint32_t a, uint32_t x, uint32_t y) {
  asm volatile("{\n.reg .pred q;\nsetp.ne.b32 q, %3, 0;\n@q st.shared.v2.u32 [%0], {%1,%2};\n}\n" ::"r"(a), "r"(x), "r"(y), "r"(p) : "memory");
}
__device__ __forceinline__ void st_x32(uint32_t* p, uint32_t x) {
  asm volatile("st.relaxed.gpu.global.u32 [%0], %1;" ::"l"(p), "r"(x) : "memory");
}
__device__ __forceinline__ uint32_t nz(uint32_t w) { return max(w, 1u); }
__device__ __forceinline__ uint32_t fu(float x) { return __float_as_uint(x); }
__device__ __forceinline__ float uf(uint32_t x) { return __uint_as_float(x); }

__device__ __forceinline__ void wgmma_ss_n96(float (&d)[48], uint64_t da, uint64_t db, int sc) {
  asm volatile("{\n.reg .pred p;\nsetp.ne.b32 p, %50, 0;\n"
      "wgmma.mma_async.sync.aligned.m64n96k16.f32.bf16.bf16 "
      "{%0,%1,%2,%3,%4,%5,%6,%7,%8,%9,%10,%11,%12,%13,%14,%15,%16,%17,%18,%19,%20,%21,%22,%23,%24,%25,%26,%27,%28,%29,%30,%31,%32,%33,%34,%35,%36,%37,%38,%39,%40,%41,%42,%43,%44,%45,%46,%47}, "
      "%48, %49, p, 1, 1, 0, 1;\n}\n"
      : "+f"(d[0]), "+f"(d[1]), "+f"(d[2]), "+f"(d[3]), "+f"(d[4]), "+f"(d[5]), "+f"(d[6]), "+f"(d[7]),
        "+f"(d[8]), "+f"(d[9]), "+f"(d[10]), "+f"(d[11]), "+f"(d[12]), "+f"(d[13]), "+f"(d[14]), "+f"(d[15]),
        "+f"(d[16]), "+f"(d[17]), "+f"(d[18]), "+f"(d[19]), "+f"(d[20]), "+f"(d[21]), "+f"(d[22]), "+f"(d[23]),
        "+f"(d[24]), "+f"(d[25]), "+f"(d[26]), "+f"(d[27]), "+f"(d[28]), "+f"(d[29]), "+f"(d[30]), "+f"(d[31]),
        "+f"(d[32]), "+f"(d[33]), "+f"(d[34]), "+f"(d[35]), "+f"(d[36]), "+f"(d[37]), "+f"(d[38]), "+f"(d[39]),
        "+f"(d[40]), "+f"(d[41]), "+f"(d[42]), "+f"(d[43]), "+f"(d[44]), "+f"(d[45]), "+f"(d[46]), "+f"(d[47])
      : "l"(da), "l"(db), "r"(sc));
}

__device__ __forceinline__ void wgmma_ss_n128(float (&d)[64], uint64_t da, uint64_t db, int sc) {
  asm volatile("{\n.reg .pred p;\nsetp.ne.b32 p, %66, 0;\n"
      "wgmma.mma_async.sync.aligned.m64n128k16.f32.bf16.bf16 "
      "{%0,%1,%2,%3,%4,%5,%6,%7,%8,%9,%10,%11,%12,%13,%14,%15,%16,%17,%18,%19,%20,%21,%22,%23,%24,%25,%26,%27,%28,%29,%30,%31,%32,%33,%34,%35,%36,%37,%38,%39,%40,%41,%42,%43,%44,%45,%46,%47,%48,%49,%50,%51,%52,%53,%54,%55,%56,%57,%58,%59,%60,%61,%62,%63}, "
      "%64, %65, p, 1, 1, 0, 1;\n}\n"
      : "+f"(d[0]), "+f"(d[1]), "+f"(d[2]), "+f"(d[3]), "+f"(d[4]), "+f"(d[5]), "+f"(d[6]), "+f"(d[7]),
        "+f"(d[8]), "+f"(d[9]), "+f"(d[10]), "+f"(d[11]), "+f"(d[12]), "+f"(d[13]), "+f"(d[14]), "+f"(d[15]),
        "+f"(d[16]), "+f"(d[17]), "+f"(d[18]), "+f"(d[19]), "+f"(d[20]), "+f"(d[21]), "+f"(d[22]), "+f"(d[23]),
        "+f"(d[24]), "+f"(d[25]), "+f"(d[26]), "+f"(d[27]), "+f"(d[28]), "+f"(d[29]), "+f"(d[30]), "+f"(d[31]),
        "+f"(d[32]), "+f"(d[33]), "+f"(d[34]), "+f"(d[35]), "+f"(d[36]), "+f"(d[37]), "+f"(d[38]), "+f"(d[39]),
        "+f"(d[40]), "+f"(d[41]), "+f"(d[42]), "+f"(d[43]), "+f"(d[44]), "+f"(d[45]), "+f"(d[46]), "+f"(d[47]),
        "+f"(d[48]), "+f"(d[49]), "+f"(d[50]), "+f"(d[51]), "+f"(d[52]), "+f"(d[53]), "+f"(d[54]), "+f"(d[55]),
        "+f"(d[56]), "+f"(d[57]), "+f"(d[58]), "+f"(d[59]), "+f"(d[60]), "+f"(d[61]), "+f"(d[62]), "+f"(d[63])
      : "l"(da), "l"(db), "r"(sc));
}

__device__ __forceinline__ void wgmma_ss_n40(float (&d)[20], uint64_t da, uint64_t db, int sc) {
  asm volatile("{\n.reg .pred p;\nsetp.ne.b32 p, %22, 0;\n"
      "wgmma.mma_async.sync.aligned.m64n40k16.f32.bf16.bf16 "
      "{%0,%1,%2,%3,%4,%5,%6,%7,%8,%9,%10,%11,%12,%13,%14,%15,%16,%17,%18,%19}, "
      "%20, %21, p, 1, 1, 1, 1;\n}\n"
      : "+f"(d[0]), "+f"(d[1]), "+f"(d[2]), "+f"(d[3]), "+f"(d[4]), "+f"(d[5]), "+f"(d[6]), "+f"(d[7]),
        "+f"(d[8]), "+f"(d[9]), "+f"(d[10]), "+f"(d[11]), "+f"(d[12]), "+f"(d[13]), "+f"(d[14]), "+f"(d[15]),
        "+f"(d[16]), "+f"(d[17]), "+f"(d[18]), "+f"(d[19])
      : "l"(da), "l"(db), "r"(sc));
}

__device__ __forceinline__ void wgmma_rs_n8(float (&d)[4], const uint4& a, uint64_t db, int sc) {
  asm volatile("{\n.reg .pred p;\nsetp.ne.b32 p, %9, 0;\n"
      "wgmma.mma_async.sync.aligned.m64n8k16.f32.bf16.bf16 "
      "{%0,%1,%2,%3}, "
      "{%4,%5,%6,%7}, %8, p, 1, 1, 1;\n}\n"
      : "+f"(d[0]), "+f"(d[1]), "+f"(d[2]), "+f"(d[3])
      : "r"(a.x), "r"(a.y), "r"(a.z), "r"(a.w), "l"(db), "r"(sc));
}

__device__ __forceinline__ void wgmma_rs_n16(float (&d)[8], const uint4& a, uint64_t db, int sc) {
  asm volatile("{\n.reg .pred p;\nsetp.ne.b32 p, %13, 0;\n"
      "wgmma.mma_async.sync.aligned.m64n16k16.f32.bf16.bf16 "
      "{%0,%1,%2,%3,%4,%5,%6,%7}, "
      "{%8,%9,%10,%11}, %12, p, 1, 1, 1;\n}\n"
      : "+f"(d[0]), "+f"(d[1]), "+f"(d[2]), "+f"(d[3]), "+f"(d[4]), "+f"(d[5]), "+f"(d[6]), "+f"(d[7])
      : "r"(a.x), "r"(a.y), "r"(a.z), "r"(a.w), "l"(db), "r"(sc));
}

__device__ __forceinline__ void wgmma_rs_n24(float (&d)[12], const uint4& a, uint64_t db, int sc) {
  asm volatile("{\n.reg .pred p;\nsetp.ne.b32 p, %17, 0;\n"
      "wgmma.mma_async.sync.aligned.m64n24k16.f32.bf16.bf16 "
      "{%0,%1,%2,%3,%4,%5,%6,%7,%8,%9,%10,%11}, "
      "{%12,%13,%14,%15}, %16, p, 1, 1, 1;\n}\n"
      : "+f"(d[0]), "+f"(d[1]), "+f"(d[2]), "+f"(d[3]), "+f"(d[4]), "+f"(d[5]), "+f"(d[6]), "+f"(d[7]),
        "+f"(d[8]), "+f"(d[9]), "+f"(d[10]), "+f"(d[11])
      : "r"(a.x), "r"(a.y), "r"(a.z), "r"(a.w), "l"(db), "r"(sc));
}

struct Params {
  const __nv_bfloat16 *logA, *Aim, *Cre, *Cim, *logdt, *Dskip, *x, *wphi, *wo;
  __nv_bfloat16* out;
  uint4* xs;
  long long* ts;
};

__device__ __forceinline__ uint4 tr_row(const uint4 (&v)[8], int i) {
  uint32_t o[4];
#pragma unroll
  for (int m = 0; m < 4; m++) {
    const uint4 &ra = v[2 * m], &rb = v[2 * m + 1];
    const int k = i >> 1;
    const uint32_t xa = k == 0 ? ra.x : k == 1 ? ra.y : k == 2 ? ra.z : ra.w;
    const uint32_t xb = k == 0 ? rb.x : k == 1 ? rb.y : k == 2 ? rb.z : rb.w;
    o[m] = __byte_perm(xa, xb, (i & 1) ? 0x7632 : 0x5410);
  }
  return make_uint4(o[0], o[1], o[2], o[3]);
}

struct cpx { float r, i; };
__device__ __forceinline__ cpx csq(cpx a) { return {a.r * a.r - a.i * a.i, 2.f * (a.r * a.i)}; }
__device__ __forceinline__ cpx polar(float e, float t) {
  const float m = ex2(e);
  return {m * __cosf(t), m * __sinf(t)};
}

struct KgenRaw { unsigned short la, ai, cr, ci, ldt; };
__device__ __forceinline__ KgenRaw kgen_load(const Params& P, int d, int unit, int lane) {
  const int o = d * 128 + unit * 32 + lane;
  return {__ldg((const unsigned short*)P.logA + o), __ldg((const unsigned short*)P.Aim + o), __ldg((const unsigned short*)P.Cre + o),
          __ldg((const unsigned short*)P.Cim + o), __ldg((const unsigned short*)P.logdt + d)};
}
struct hmul { __half2 a, b; };
__device__ __forceinline__ hmul mk_mul(cpx w) {
  uint32_t b;
  asm("{\n.reg .f32 n;\nneg.ftz.f32 n, %1;\ncvt.rn.f16x2.f32 %0, %2, n;\n}\n" : "=r"(b) : "f"(w.i), "f"(w.r));
  return {__floats2half2_rn(w.r, w.i), *(const __half2*)&b};
}
__device__ __forceinline__ __half2 hcm(__half2 z, const hmul& w) { return __hfma2(__high2half2(z), w.b, __hmul2(__low2half2(z), w.a)); }
__device__ __forceinline__ uint32_t hu(__half2 v) { return *(const uint32_t*)&v; }

struct KgenAddr { uint32_t sa, lb, lm[4]; };
__device__ __forceinline__ KgenAddr kgen_addr(int lane, uint32_t buf) {
  KgenAddr a;
  a.sa = buf + (lane & 7) * 128 + ((((lane >> 3) ^ lane) & 7) << 4);
  const int q = lane >> 3;
  a.lb = buf + q * 128 + (((lane ^ q) & 7) << 4);
  a.lm[0] = buf + q * 128 + (q << 4);
  a.lm[1] = buf + q * 128 + ((1 ^ q) << 4);
  a.lm[2] = buf + q * 128 + (((2 + (lane & 1)) ^ q) << 4);
  a.lm[3] = buf + q * 128 + (((4 + (lane & 3)) ^ q) << 4);
  asm volatile("" : "+r"(a.sa), "+r"(a.lb), "+r"(a.lm[0]), "+r"(a.lm[1]), "+r"(a.lm[2]), "+r"(a.lm[3]));
  return a;
}
__device__ __forceinline__ void kgen_unit(const KgenRaw& r, const KgenAddr& ad, uint32_t zero, float (&k)[5][4], float& k2048, float& sc) {
  const float dt = bf_round(expf(bf_lo(r.ldt)));
  const float a2 = bf_round(ex2(bf_lo(r.la) * 1.4426950408889634f)) * (dt * -1.4426950408889634f);
  const float f = bf_lo(r.ai) * dt;
  const float r127 = f * 20.21267777267071f;
  const uint32_t ex = min(max(__reduce_max_sync(0xffffffffu, max(r.cr & 0x7fffu, r.ci & 0x7fffu)) >> 7, 1u), 253u);
  const float cs = uf((254u - ex) << 23);
  sc = 2.f * dt * uf(ex << 23);
  const cpx C = {bf_lo(r.cr) * cs, -bf_lo(r.ci) * cs};
  auto put = [&](const __half2 (&v)[8]) {
    stsm4(ad.sa, hu(v[0]), hu(v[1]), hu(v[2]), hu(v[3]));
    stsm4(ad.sa ^ 64, hu(v[4]), hu(v[5]), hu(v[6]), hu(v[7]));
    __syncwarp();
  };
  auto get = [&](uint32_t (&o)[2][4], uint32_t a) { ldsm4(o[0], a); ldsm4(o[1], (a ^ 64) + 512); };
  auto rot = [](uint32_t z) { return __byte_perm(z, z, 0x1032) ^ 0x8000u; };
  auto fmul = [](uint32_t z, uint32_t zi, uint32_t w) {
    const __half2 hw = *(const __half2*)&w;
    return hu(__hfma2(*(const __half2*)&zi, __high2half2(hw), __hmul2(*(const __half2*)&z, __low2half2(hw))));
  };
  uint32_t A[4][4];
  auto tile = [&](int j, const uint32_t (&B)[2][4]) {
    k[j][0] = k[j][1] = k[j][2] = k[j][3] = 0.f;
#pragma unroll
    for (int s = 0; s < 4; s++) mma_h(k[j], A[s], B[s >> 1][2 * (s & 1)], B[s >> 1][2 * (s & 1) + 1]);
  };
  auto after = [&](cpx v, uint32_t dep) { return cpx{uf(fu(v.r) ^ (dep & zero)), v.i}; };
  const cpx w1 = polar(a2, f), w127 = polar(a2 * 127.f, (r127 - rintf(r127)) * 6.283185307179586f);
  const cpx w2 = csq(w1), w4 = csq(w2);
  uint32_t T0[2][4], A0[2][4], T4[2][4], M[4][2][4];
  {
    __half2 t[8];
    const hmul m2 = mk_mul(w2), m4 = mk_mul(w4);
    t[0] = __floats2half2_rn(1.f, 0.f); t[1] = __floats2half2_rn(w1.r, w1.i); t[2] = m2.a; t[4] = m4.a;
    t[3] = hcm(t[1], m2); t[5] = hcm(t[1], m4); t[6] = hcm(t[2], m4); t[7] = hcm(t[3], m4);
    put(t); get(T0, ad.lb);
  }
  cpx w8 = csq(w4);
  w8.i = -w8.i;
  const cpx w16 = csq(w8), w32 = csq(w16), w64 = csq(w32);
  {
    const hmul m8 = mk_mul(w8), m16 = mk_mul(w16), m32 = mk_mul(w32);
    __half2 a[8];
    a[0] = __floats2half2_rn(C.r, C.i); a[1] = hcm(a[0], m8);
    a[2] = hcm(a[0], m16); a[3] = hcm(a[1], m16);
#pragma unroll
    for (int i = 0; i < 4; i++) a[4 + i] = hcm(a[i], m32);
    put(a); get(A0, ad.lb);
  }
  const cpx w127b = after(w127, T0[0][0]);
  const cpx w128 = {w127b.r * w1.r - w127b.i * w1.i, w127b.r * w1.i + w127b.i * w1.r};
  const cpx w256 = csq(w128), w512 = csq(w256);
  const hmul m128 = mk_mul(w128), m256 = mk_mul(w256), m512 = mk_mul(w512);
  {
    const hmul m254 = mk_mul(csq(w127b));
    const __half2 h127 = __floats2half2_rn(w127b.r, w127b.i);
    __half2 m[8];
    m[0] = __floats2half2_rn(w64.r, w64.i); m[1] = m128.a; m[2] = m256.a; m[3] = hcm(h127, m256);
    m[4] = m512.a; m[5] = hcm(h127, m512); m[6] = hcm(m[4], m254); m[7] = hcm(m[5], m254);
    put(m);
#pragma unroll
    for (int i = 0; i < 4; i++) get(M[i], ad.lm[i]);
  }
  const cpx w1024 = csq(after(w512, A0[0][0])), we = csq(w1024);
  {
    __half2 t[8];
    t[0] = __floats2half2_rn(w1024.r, w1024.i); t[1] = hcm(t[0], m128);
    t[2] = hcm(t[0], m256); t[3] = hcm(t[1], m256);
#pragma unroll
    for (int i = 0; i < 4; i++) t[4 + i] = hcm(t[i], m512);
    put(t); get(T4, ad.lb);
  }
  k2048 = (C.r * we.r + C.i * we.i) * sc;
#pragma unroll
  for (int i = 0; i < 8; i++) {
    const uint32_t z = A0[i >> 2][i & 3];
    A[i >> 1][2 * (i & 1)] = z;
    A[i >> 1][2 * (i & 1) + 1] = fmul(z, rot(z), M[0][i >> 2][i & 3]);
  }
  tile(0, T0);
#pragma unroll
  for (int i = 0; i < 8; i++) {
    const uint32_t z = T0[i >> 2][i & 3], zi = rot(z);
#pragma unroll
    for (int j = 1; j < 4; j++) M[j][i >> 2][i & 3] = fmul(z, zi, M[j][i >> 2][i & 3]);
  }
  tile(4, T4); tile(1, M[1]); tile(2, M[2]); tile(3, M[3]);
}

__device__ __forceinline__ void build_tables(uint32_t tb, int lane, float (&k)[5][4], float k2048) {
  const int g = lane >> 2, c = lane & 3;
  const uint32_t kc = tb + T_KC + 16;
  {
    const uint32_t a0 = kc + 16 * g + 4 * c, a2 = kc + 2 * (256 + 4 * g + c);
    const uint32_t a3 = kc + 2 * (384 + 2 * g + 64 * (c & 1) + (c >> 1)), a4 = kc + 2 * (512 + g + 32 * c);
#pragma unroll
    for (int r = 0; r < 2; r++) {
      sts32(a0 + 128 * r, pack_bf(k[0][2 * r], k[0][2 * r + 1]));
      sts32(a0 + 128 * r + 256, pack_bf(k[1][2 * r], k[1][2 * r + 1]));
      const uint32_t w2 = pack_bf(k[2][2 * r], k[2][2 * r + 1]);
      const uint32_t w3 = pack_bf(k[3][2 * r], k[3][2 * r + 1]);
      const uint32_t w4 = pack_bf(k[4][2 * r], k[4][2 * r + 1]);
      sts16(a2 + 64 * r, w2); sts16(a2 + 64 * r + 128, w2 >> 16);
      sts16(a3 + 32 * r, w3); sts16(a3 + 32 * r + 64, w3 >> 16);
      sts16(a4 + 16 * r, w4); sts16(a4 + 16 * r + 32, w4 >> 16);
    }
  }
  if (lane == 0) { sts16(kc + 2 * 640, pack_bf(k2048, 0.f)); sts32(kc - 4, 0); }
  __syncwarp();
  const uint32_t td = tb + T_D + 32;
#pragma unroll
  for (int hf = 0; hf < 2; hf++) {
    const uint2 v = lds64(kc + 256 * hf + 8 * lane);
    const uint32_t pv = lds32(kc + 256 * hf + 8 * lane - 4);
    sts128(td + 512 * hf + 16 * lane, __byte_perm(v.x, pv, 0x7610), __byte_perm(v.x, v.x, 0x1032), __byte_perm(v.y, v.x, 0x7610),
           __byte_perm(v.y, v.y, 0x1032));
  }
#pragma unroll
  for (int hf = 0; hf < 2; hf++) {
    const uint32_t v = lds32(kc + 512 + 128 * hf + 4 * lane), nx = lds32(kc + 516 + 128 * hf + 4 * lane);
    uint32_t w0 = __byte_perm(v, v, 0x1010);
    const uint32_t w1 = w0;
    if (hf == 0) { const uint32_t pv = lds32(kc + 508); if (lane == 0) w0 = __byte_perm(v, pv, 0x7610); }
    sts128(td + 1024 + 512 * hf + 16 * lane, w0, w1, __byte_perm(v, v, 0x1032), __byte_perm(nx, v, 0x7610));
  }
  {
    const uint32_t kk = lds16(kc + 2 * 384);
    const uint32_t w = lane < 3 ? (kk | (kk << 16)) : (lane == 3 ? (kk << 16) : 0u);
    if (lane < 24) sts32(td + 4 * (lane < 16 ? 512 + lane : lane - 24), w);
    const uint32_t lo_ = lds16(kc + 2 * 511), le_ = lds16(kc + 2 * 512);
    const uint32_t ja = tb + T_5 + (lane < 16 ? 4 * lane : 256 + 4 * lane);
    sts32(ja, lane == 16 ? (le_ << 16) : 0u);
    sts32(ja + 384, lane == 16 ? (lo_ << 16) : 0u);
    sts32(tb + (lane < 16 ? T_7 : T_9 - 64) + 4 * lane, 0u);
  }
#pragma unroll
  for (int s = 0; s < 2; s++) {
    const uint32_t b = kc + 2 * (s ? 512 : 384) + 8 * lane;
    const uint2 v = lds64(b);
    uint32_t em = lds16(b - 2), e0 = v.x;
    const uint32_t e4 = lds16(b + 8);
    if (lane == 0) { em = 0; e0 = 0; }
    sts64(tb + (s ? T_7 : T_3) + 64 + 8 * lane, __byte_perm(v.x, em, 0x5432), __byte_perm(v.y, v.x, 0x7632));
    sts64(tb + (s ? T_9 : T_5) + 64 + 8 * lane, __byte_perm(v.y, e0, 0x5410), __byte_perm(e4, v.y, 0x5410));
  }
  __syncwarp();
}

__device__ __forceinline__ uint32_t box2w(int lo, int n, int o) {
  return ((unsigned)(o - lo) < (unsigned)n ? 0x3F80u : 0u) | ((unsigned)(o + 1 - lo) < (unsigned)n ? 0x3F800000u : 0u);
}

__device__ __forceinline__ void conv_channel(uint32_t ub, uint32_t tb, int lane, uint4* ydst) {
  const int g = lane >> 2, c = lane & 3, x = g - 2 * c;
  const int mi = lane >> 3;
  const uint32_t qa = ub + U_PAD + 16 * (lane & 7) + ((mi == 0 || mi == 3) ? U_ODD : 0) - (mi == 0 ? 16 : 0);
  const uint32_t hb = ub + U_PAD + (mi & 1) * U_ODD + 16 * ((lane >> 4) + (lane & 7)) - 16;
  const uint32_t kv = lds16(tb + T_KC + 16 + 2 * 512);
  const int oh = c < 2 ? 8 + 2 * c : 2 * c - 8, og = c < 3 ? 2 * c : -10;
  uint32_t bx[4] = {box2w(g - 4, 9, 2 * c), box2w(g - 3, 7, 2 * c), box2w(g - 4, 9, oh), box2w(g - 3, 7, oh)};
  uint32_t by[4] = {box2w(g - 10, 5, 2 * c - 8), box2w(g - 5, 3, 2 * c - 8), box2w(g - 10, 5, og), box2w(g - 5, 3, og)};
  uint32_t lb0 = ((unsigned)(x + 5) < 2u ? kv : 0u) | ((unsigned)(x + 4) < 2u ? kv << 16 : 0u);
  uint32_t lb1 = ((unsigned)(x - 3) < 2u ? kv : 0u) | ((unsigned)(x - 4) < 2u ? kv << 16 : 0u);
  const int q0 = g - 1, q1 = c < 3 ? g : g - 2;
  uint32_t y0a = ub + U_PAD + (q0 & 1) * U_ODD + 16 * (q0 >> 1) + 4 * c;
  uint32_t y1a = ub + U_PAD + (q1 & 1) * U_ODD + 16 * (q1 >> 1) + 4 * c;
#pragma unroll
  for (int i = 0; i < 4; i++) asm volatile("" : "+r"(bx[i]), "+r"(by[i]));
  asm volatile("" : "+r"(lb0), "+r"(lb1), "+r"(y0a), "+r"(y1a));
  mbar_wait(BAR(MB_UFULL));
  mbar_spin(BAR(MB_EMPTY + 15));
  nb_sync(NB_GATE, 256);
  SPLIT();
  TS(36);
  float acc[16][4];
  {
    uint32_t z09[8], z07[8], zm9[8], zm7[8];
#pragma unroll
    for (int i = 0; i < 8; i++) {
      uint32_t h[4];
      ldsm4(h, hb + 128 * i);
      float y0, y1, y2, y3, w0, w1, w2, w3;
      mma0(y0, y1, y2, y3, bx[0], bx[1], bx[2], bx[3], h[2], c < 2 ? h[3] : h[1]);
      mma0(w0, w1, w2, w3, bx[0], bx[1], bx[2], bx[3], h[1], c < 2 ? h[2] : h[0]);
      z09[i] = pack_bf(y0, y1); z07[i] = pack_bf(y2, y3);
      zm9[i] = pack_bf(w0, w1); zm7[i] = pack_bf(w2, w3);
    }
  uint32_t f3[3][4][4];
  {
    const uint32_t fa = tb + T_7 + 4 * (16 + x);
#pragma unroll
    for (int tt = 0; tt < 3; tt++)
#pragma unroll
      for (int D = 0; D < 4; D++) {
        const uint32_t a = fa + (tt == 0 ? 316 : (tt == 1 ? 320 : 0)) + 64 * D;
        f3[tt][D][0] = lds32(a); f3[tt][D][1] = lds32(a + 32); f3[tt][D][2] = lds32(a - 32); f3[tt][D][3] = lds32(a);
      }
  }
    float a[4][2][4];
#pragma unroll
    for (int kap = 0; kap < 4; kap++)
#pragma unroll
      for (int sg = 0; sg < 2; sg++)
#pragma unroll
        for (int bk = 3; bk >= kap; bk--) {
          const uint32_t(&q0_)[4] = f3[sg ? 2 : 0][bk - kap];
          const uint32_t(&q1_)[4] = f3[sg ? 2 : 1][bk - kap];
          float(&a0)[4] = a[bk][0];
          float(&a1)[4] = a[bk][1];
          if (sg == 0 && kap == 0) {
            mma0(a0[0], a0[1], a0[2], a0[3], q0_[0], q0_[1], q0_[2], q0_[3], z09[0], z09[1]);
            mma0(a1[0], a1[1], a1[2], a1[3], q1_[0], q1_[1], q1_[2], q1_[3], zm9[0], zm9[1]);
          } else {
            mma(a0[0], a0[1], a0[2], a0[3], q0_[0], q0_[1], q0_[2], q0_[3], sg ? zm7[2 * kap] : z09[2 * kap], sg ? zm7[2 * kap + 1] : z09[2 * kap + 1]);
            mma(a1[0], a1[1], a1[2], a1[3], q1_[0], q1_[1], q1_[2], q1_[3], sg ? z07[2 * kap] : zm9[2 * kap], sg ? z07[2 * kap + 1] : zm9[2 * kap + 1]);
          }
        }
    SPLIT();
#pragma unroll
    for (int i = 0; i < 8; i++) {
      uint32_t h[4];
      ldsm4(h, qa + 128 * i);
      const float ci[4] = {a[i >> 1][0][2 * (i & 1)], a[i >> 1][0][2 * (i & 1) + 1], a[i >> 1][1][2 * (i & 1)], a[i >> 1][1][2 * (i & 1) + 1]};
      mmac(acc[8 + i], h[0], h[1], h[2], h[3], lb0, lb1, ci);
    }
  }
  TS(44);
  {
    uint2 a5[10], a3[10];
    const uint32_t aa = tb + T_5 + 4 * (8 + 2 * g - 2 * c);
#pragma unroll
    for (int m = 0; m < 10; m++) { a5[m] = lds64(aa + 32 * m); a3[m] = lds64(aa + 384 + 32 * m); }
    uint32_t x5[12][2], x3[12][2];
    auto ygen = [&](int kap) {
#pragma unroll
      for (int hh = 0; hh < 2; hh++) {
        float y0, y1, y2, y3;
        mma0(y0, y1, y2, y3, by[0], by[1], by[2], by[3], lds32(y0a + 128 * kap + 64 * hh), lds32(y1a + 128 * kap + 64 * hh));
        x5[kap][hh] = pack_bf(y0, y1);
        x3[kap][hh] = pack_bf(y2, y3);
      }
    };
    ygen(11); ygen(10); ygen(9); ygen(8);
#pragma unroll
    for (int kap = 11; kap >= 0; kap--) {
      if (kap >= 4) ygen(kap - 4);
#pragma unroll
      for (int sg = 0; sg < 2; sg++)
#pragma unroll
        for (int i = 4; i >= 0; i--) {
          const int be = kap + 4 + i;
          if (be <= 15) {
            const uint2 &hi = sg ? a3[2 * i + 1] : a5[2 * i + 1], &lo = sg ? a3[2 * i] : a5[2 * i];
            const uint32_t b0 = sg ? x3[kap][0] : x5[kap][0], b1 = sg ? x3[kap][1] : x5[kap][1];
            if (be < 8 && i == 0 && sg == 0) mma0(acc[be][0], acc[be][1], acc[be][2], acc[be][3], hi.x, hi.y, lo.x, lo.y, b0, b1);
            else mma(acc[be][0], acc[be][1], acc[be][2], acc[be][3], hi.x, hi.y, lo.x, lo.y, b0, b1);
          }
        }
    }
  }
  TS(45);
  {
    const uint32_t st = tb + T_ST + lane * 8;
#pragma unroll
    for (int be = 4; be < 12; be++) sts64(st + 256 * be, pack_bf(acc[be][0], acc[be][1]), pack_bf(acc[be][2], acc[be][3]));
    SPLIT();
    uint32_t F[66], qd[8][4];
    const uint32_t fa = tb + T_D + 32 + 4 * x;
#pragma unroll
    for (int i = 0; i < 32; i++) {
      const int s = 120 - (i >> 2) - 8 * (i & 3);
      uint32_t(&q)[4] = qd[i & 7];
      ldsm4(q, qa + 16 * s);
      const int m = 16 * (i & 3) + 2 * (i >> 2);
      F[m] = lds32(fa + 32 * m); F[m + 1] = lds32(fa + 32 * m + 32);
#pragma unroll
      for (int be = 15; be >= 12; be--) {
        const int de = 8 * be - s;
        float(&a)[4] = (be >= 14 && !(i & 1)) ? acc[be - 4] : acc[be];
        if (de >= 0 && be >= 14 && i == 2 * (15 - be)) mma0(a[0], a[1], a[2], a[3], q[0], q[1], q[2], q[3], F[2 * de + 1], F[2 * de]);
        else if (de >= 0) mma(a[0], a[1], a[2], a[3], q[0], q[1], q[2], q[3], F[2 * de + 1], F[2 * de]);
      }
    }
#pragma unroll
    for (int i = 0; i < 8; i++) acc[14 + (i >> 2)][i & 3] += acc[10 + (i >> 2)][i & 3];
    F[64] = lds32(fa + 32 * 64); F[65] = lds32(fa + 32 * 65);
#pragma unroll
    for (int i = 0; i < 6; i++) ldsm4(qd[i], qa + 128 * 11 - 16 * i);
    uint2 sv = lds64(st + 256 * 11);
    float ci[4] = {bf_lo(sv.x), bf_hi(sv.x), bf_lo(sv.y), bf_hi(sv.y)};
    float T[5][4];
#pragma unroll
    for (int i = 0; i < 16; i++) T[i >> 2][i & 3] = acc[12 + (i >> 2)][i & 3];
    nb_sync(NB_YZ, 160);
    TS(46);
    uint32_t held[2];
#pragma unroll
    for (int be = 11; be >= 0; be--) {
      if (be & 1) SPLITN(be);
      const uint32_t qp = qa + 128 * be;
#pragma unroll
      for (int k = 4; k >= 1; k--) mmac(T[k], qd[0][0], qd[0][1], qd[0][2], qd[0][3], F[16 * k + 1], F[16 * k], T[k - 1]);
      if (be >= 4) mmac(T[0], qd[0][0], qd[0][1], qd[0][2], qd[0][3], F[1], F[0], ci);
      else mma0(T[0][0], T[0][1], T[0][2], T[0][3], qd[0][0], qd[0][1], qd[0][2], qd[0][3], F[1], F[0]);
      ldsm4(qd[6], qp - 16 * 6);
      ldsm4(qd[7], qp - 16 * 7);
      if (be > 4) sv = lds64(st + 256 * (be - 1));
#pragma unroll
      for (int i = 1; i < 8; i++) {
#pragma unroll
        for (int k = 3; k >= 0; k--)
          mma(T[k][0], T[k][1], T[k][2], T[k][3], qd[i][0], qd[i][1], qd[i][2], qd[i][3], F[16 * k + 2 * i + 1], F[16 * k + 2 * i]);
        if (i < 7 && be > 0) ldsm4(qd[i - 1], qp - 128 - 16 * (i - 1));
        if (i == 2) {
          const uint32_t w0 = pack_bf(T[4][0], T[4][1]), w1 = pack_bf(T[4][2], T[4][3]);
          if (be & 1) { held[0] = w0; held[1] = w1; }
          else st_x(ydst + (be + 4) * 16, nz(w0), w1, held[0], held[1]);
          if ((be & 3) == 3 && be < 11) nb_arrive(NB_Y + 2 + (be >> 2), 160);
        }
        if (i == 4 && be > 4) { ci[0] = bf_lo(sv.x); ci[1] = bf_hi(sv.x); ci[2] = bf_lo(sv.y); ci[3] = bf_hi(sv.y); }
      }
    }
    nb_arrive(NB_Y + 1, 160);
#pragma unroll
    for (int B = 1; B >= 0; B--)
      st_x(ydst + B * 32, nz(pack_bf(T[2 * B][0], T[2 * B][1])), pack_bf(T[2 * B][2], T[2 * B][3]),
           pack_bf(T[2 * B + 1][0], T[2 * B + 1][1]), pack_bf(T[2 * B + 1][2], T[2 * B + 1][3]));
  }
}

__device__ __forceinline__ void dual_exp(const uint32_t* w, uint32_t* e) {
  const float L = 1.44268798828125f;
  uint32_t mx = bmax2(bmax2(w[0], w[1]), bmax2(w[2], w[3]));
  uint32_t mn = bmin2(bmin2(w[0], w[1]), bmin2(w[2], w[3]));
  mx = bmax2(mx, __shfl_xor_sync(0xffffffffu, mx, 1));
  mn = bmin2(mn, __shfl_xor_sync(0xffffffffu, mn, 1));
  mx = bmax2(mx, __shfl_xor_sync(0xffffffffu, mx, 2));
  mn = bmin2(mn, __shfl_xor_sync(0xffffffffu, mn, 2));
  const float mx0 = bf_lo(mx) * -L, mx1 = bf_hi(mx) * -L, mn0 = bf_lo(mn) * L, mn1 = bf_hi(mn) * L;
#pragma unroll
  for (int i = 0; i < 2; i++) {
    const float a0 = bf_lo(w[2 * i]), a1 = bf_hi(w[2 * i]), b0 = bf_lo(w[2 * i + 1]), b1 = bf_hi(w[2 * i + 1]);
    e[2 * i] = pack_bf(ex2(fmaf(a0, L, mx0)), ex2(fmaf(b0, L, mx0)));
    e[2 * i + 1] = pack_bf(ex2(fmaf(a1, L, mx1)), ex2(fmaf(b1, L, mx1)));
    e[4 + 2 * i] = pack_bf(ex2(fmaf(a0, -L, mn0)), ex2(fmaf(b0, -L, mn0)));
    e[5 + 2 * i] = pack_bf(ex2(fmaf(a1, -L, mn1)), ex2(fmaf(b1, -L, mn1)));
  }
}
__device__ __forceinline__ void normalise(uint32_t* e, const float (&s)[4]) {
  const uint32_t r = pack_bf(rcp(s[0]), rcp(s[2]));
  const __nv_bfloat162 rr = *(const __nv_bfloat162*)&r;
#pragma unroll
  for (int i = 0; i < 4; i++) {
    const __nv_bfloat162 v = __hmul2(*(const __nv_bfloat162*)&e[i], (i & 1) ? __high2bfloat162(rr) : __low2bfloat162(rr));
    e[i] = *(const uint32_t*)&v;
  }
}
__host__ __device__ constexpr uint64_t qdesc(uint32_t addr) { return mkdesc(addr, 128, 256, 0); }

__global__ void __launch_bounds__(NTHREADS, 1)
fused_kernel(const Params P, const __grid_constant__ CUtensorMap mx, const __grid_constant__ CUtensorMap mw,
             const __grid_constant__ CUtensorMap mo, const __grid_constant__ CUtensorMap mu,
             const __grid_constant__ CUtensorMap mout, const __grid_constant__ CUtensorMap mw4) {
  constexpr uint32_t sb = SB;
  const int tid = threadIdx.x, lane = tid & 31;
  const int warp = __shfl_sync(0xffffffffu, tid >> 5, 0);
  const int b = blockIdx.x, oct = b >> 3, i8 = b & 7;
  const int rt = (((oct & 4) ? ~oct : oct) & 3) * 2 + (i8 >> 2);
  const int hp = (oct >> 2) * 4 + (i8 & 3);

  const int wg = warp >> 2, w = warp & 3;
  const int d = b * 4 + ((tid >> 5) & 3);
  const KgenRaw raw = kgen_load(P, d, tid >> 7, lane);
  const unsigned short dsk = __ldg((const unsigned short*)P.Dskip + d);
  if (warp == 15) {
    asm volatile("prefetch.tensormap [%0];" ::"l"(&mu) : "memory");
    asm volatile("prefetch.tensormap [%0];" ::"l"(&mw) : "memory");
    asm volatile("prefetch.tensormap [%0];" ::"l"(&mx) : "memory");
    asm volatile("prefetch.tensormap [%0];" ::"l"(&mw4) : "memory");
  }
  if (warp == 12) {
    if (lane == 0) {
#pragma unroll
      for (int i = 0; i < 9; i++) mbar_init(BAR(i), 1);
      asm volatile("fence.mbarrier_init.release.cluster;" ::: "memory");
    }
    __syncwarp();
    if (lane < 9) mbar_expect(BAR(0) + 8 * lane, (lane == 5 || lane == 7) ? 40960 : ((lane == 0 || lane > 5) ? 16384 : 28672));
    __syncwarp();
    e_tma3d(sb + OFF_W, &mw, BAR(MB_FULL), hp * 32, 0, 0);
    e_tma2d(sb + OFF_X + 3 * 16384, &mx, BAR(MB_FULL), 0, rt * 256);
    nb_arrive(NB_PROD, 512);
  } else if (warp == 14) {
    e_prefetch(P.x + (size_t)(rt * 256 + hp * 8) * 512, 8192);
  } else if (warp == 13) {
    if (lane == 0) {
#pragma unroll
      for (int i = 9; i < 40; i++) mbar_init(BAR(i), i < MB_EMPTY ? 1 : 4);
      asm volatile("fence.mbarrier_init.release.cluster;" ::: "memory");
    }
    __syncwarp();
    if (lane < 14 && lane != 9) mbar_expect(BAR(MB_FULL + 8) + 8 * lane, lane == 8 ? 131072 : (lane == 10 ? 8192 : (lane == 13 ? 24576 : 16384)));
    nb_arrive(NB_PROD, 512);
  }
  const uint32_t tb = sb + OFF_T + w * T_CH;
  const uint32_t kp = wg == 2 ? sb + OFF_STG0 + 16384 + w * 1024 : ((tb + 127) & ~127u) + (wg == 3 ? 2 : wg) * 1536;
  const KgenAddr kad = kgen_addr(lane, kp);
  if ((warp >> 1) != 6) nb_sync(NB_PROD, 512);
  else nb_sync(NB_GATE + 1, 64);
  if (warp == 12) {
#pragma unroll 1
    for (int kb = 1; kb < 4; kb++) {
      if (kb == U_AT) e_tma4d(sb + OFF_STG0, &mu, BAR(MB_URAW), i8 * 64, oct * 2);
      e_tma3d(sb + OFF_W + kb * 12288, &mw, BAR(MB_FULL) + 8 * kb, hp * 32, kb * 64, 0);
      e_tma2d(sb + OFF_X + (kb < 2 ? kb + 3 : kb - 2) * 16384, &mx, BAR(MB_FULL) + 8 * kb, kb * 64, rt * 256);
    }
    e_tma4d(sb + OFF_W + 4 * 12288, &mw4, BAR(MB_FULL + 4), hp * 32, 4);
    e_tma2d(sb + OFF_X + 2 * 16384, &mx, BAR(MB_FULL + 4), 256, rt * 256);
    e_tma4d(sb + OFF_W + 6 * 12288, &mw4, BAR(MB_FULL + 6), hp * 32, 6);
    if (smem_u32(smem_raw) != SB) __trap();
    if (lane == 0) TS1(54);
  }
  float k[5][4], k2048, ksc;
  kgen_unit(raw, kad, blockIdx.y, k, k2048, ksc);
  TS(40 + wg);
  if ((fu(k[0][0]) & fu(k[1][0]) & fu(k[2][0]) & fu(k[3][0]) & fu(k[4][0])) == 0xffffffffu) sts32(kp, 0);
  if (wg) nb_arrive(0, 512);
  k2048 += __shfl_xor_sync(0xffffffffu, k2048, 16);
  k2048 += __shfl_xor_sync(0xffffffffu, k2048, 8);
  if (wg != 2) {
    uint32_t h[10];
#pragma unroll
    for (int j = 0; j < 10; j++) h[j] = hu(__floats2half2_rn(k[j >> 1][2 * (j & 1)], k[j >> 1][2 * (j & 1) + 1]));
    sts128(kp + lane * 16, h[0], h[1], h[2], h[3]);
    sts128(kp + 512 + lane * 16, h[4], h[5], h[6], h[7]);
    sts128(kp + 1024 + lane * 16, h[8], h[9], fu(k2048), fu(ksc));
  }
  if (wg == 0) { nb_arrive(NB_PREP, 512); nb_sync(0, 512); }
  else if (wg != 2) nb_arrive(NB_PREP, 512);
  else nb_sync(NB_PREP, 512);
  if (warp >= 12) {
    asm volatile("setmaxnreg.dec.sync.aligned.u32 32;");
    if (warp == 12) {
      if (X2_AT < 0) e_prefetch(P.x + (size_t)(rt * 256 + 128 + hp * 8) * 512, 8192);
      uint32_t slot = sb + OFF_X + 3 * 16384;
#pragma unroll 1
      for (int n = 0; n < 11; n++) {
        mbar_spin(BAR(MB_EMPTY) + 8 * n);
        const int m = n + 5;
        e_tma2d(slot, &mx, BAR(MB_FULL) + 8 * m, (m & 7) * 64, rt * 256 + (m >> 3) * 128);
        slot = slot == sb + OFF_X + 4 * 16384 ? sb + OFF_X : slot + 16384;
        if (n == X2_AT) e_prefetch(P.x + (size_t)(rt * 256 + 128 + hp * 8) * 512, 8192);
        if (n == 7) {
          e_prefetch(P.wo + (size_t)b * 2048, 4096);
          asm volatile("prefetch.tensormap [%0];" ::"l"(&mo) : "memory");
          asm volatile("prefetch.tensormap [%0];" ::"l"(&mout) : "memory");
        }
      }
#pragma unroll 1
      for (int i = 0; i < 8; i++) {
        mbar_wait(BAR(MB_EMPTY + 10) + 8 * ((0x54332222u >> (4 * i)) & 7));
        const int w0 = (0x54736210u >> (4 * i)) & 7;
        e_tma3d(sb + OFF_W + w0 * 16384, &mo, BAR(MB_WO), 0, w0 * 64, (hp & 3) * 2);
      }
    } else {
      if (warp == 15) {
        const uint4 v0 = __ldg((const uint4*)P.wphi + hp * 64 + lane), v1 = __ldg((const uint4*)P.wphi + hp * 64 + 32 + lane);
        sts128(sb + OFF_PHI + (lane & 1) * 256 + (lane >> 1) * 16, v0.x, v0.y, v0.z, v0.w);
        sts128(sb + OFF_PHI + 512 + (lane & 1) * 256 + (lane >> 1) * 16, v1.x, v1.y, v1.z, v1.w);
        const uint32_t one = (((lane >> 3) ^ (lane >> 4)) & 1) ? 0u : ((lane & 1) ? 0x3F800000u : 0x3F80u);
        const int q = (lane >> 1) & 3;
        sts128(sb + OFF_EYE + lane * 16, q == 0 ? one : 0u, q == 1 ? one : 0u, q == 2 ? one : 0u, q == 3 ? one : 0u);
        sts64(sb + OFF_ONE + lane * 8, 0x3F803F80u, 0x3F803F80u);
        asm volatile("fence.proxy.async.shared::cta;" ::: "memory");
        nb_arrive(NB_KREAD, 160);
      }
      uint32_t* cnt = (uint32_t*)(P.xs + X_CNT) + (warp == 13 ? i8 : (warp == 14 ? 8 + rt : 16 + oct)) * 32;
      const unsigned target = (ld_x32(cnt) & ~15u) + 16;
      if (warp != 14) {
        if (warp == 15) mbar_wait(BAR(MB_EMPTY + ZERO_STEP));
        uint4* pz = P.xs + (warp == 13 ? X_PART + (hp * 8 + rt) * 144 : X_Y + b * 1024) + lane;
#pragma unroll 1
        for (int i = (warp == 13 ? 144 : 1024) - lane; i > 0; i -= 32, pz += 32) st_x(pz, 0, 0, 0, 0);
      }
      if (warp == 15) __syncwarp();
      else nb_sync(warp == 13 ? NB_INIT : NB_ODONE, warp == 13 ? 160 : 288);
      if (lane == 0) asm volatile("red.release.gpu.global.add.u32 [%0], %1;" ::"l"(cnt), "r"(warp == 15 ? 2 : 1) : "memory");
      if (lane == 0) TS1(warp == 13 ? 50 : (warp == 14 ? 57 : 53));
      __syncwarp();
      if (warp == 14) nb_arrive(NB_GATE + 1, 160);
      asm volatile("fence.proxy.async.shared::cta;" ::: "memory");
      if (warp == 13) cnt += ((lane & 1 ? b >> 4 : i8 ^ (lane & 4)) - i8) * 32;
#pragma unroll 1
      for (int i = 0; i < SPIN_MAX; i++) {
        unsigned v;
        asm volatile("ld.acquire.gpu.global.u32 %0, [%1];" : "=r"(v) : "l"(cnt) : "memory");
        if (__all_sync(0xffffffffu, (int)(v - target) >= 0)) break;
      }
      if (lane == 0) TS1(warp == 13 ? 51 : (warp == 14 ? 58 : 55));
      if (warp == 15) { nb_arrive(NB_YZ, 160); return; }
      asm volatile("fence.proxy.async.global;" ::: "memory");
      if (warp == 13) {
        mbar_wait(BAR(MB_EMPTY + 11));
        e_expect(BAR(MB_UFULL), 4 * U_CH);
        e_bulk(sb + OFF_U, P.xs + X_UT + b * (U_CH / 4), 4 * U_CH, BAR(MB_UFULL));
      } else {
        const uint4* src = P.xs + X_O + (rt * 4 + (hp >> 2)) * 4096;
        e_bulk(sb + OFF_X + 32768 + 57344, src + 3584, 8192, BAR(MB_O));
        e_bulk(sb + OFF_X + 32768, src, 16384, BAR(MB_O + 1));
        e_bulk(sb + OFF_X + 49152, src + 1024, 16384, BAR(MB_O + 2));
        e_bulk(sb + OFF_STG0, src + 3200, 6144, BAR(MB_O + 3));
        nb_sync(NB_BDONE, 288);
        asm volatile("fence.proxy.async.shared::cta;" ::: "memory");
        e_bulk(sb + OFF_U, src + 2048, 18432, BAR(MB_O + 3));
      }
    }
    return;
  }

  const int t = tid & 127;
  const int g = lane >> 2, c = lane & 3;
  if (wg == 1) {
    mbar_wait(BAR(MB_URAW));
    TS(48);
    uint4* dst = P.xs + X_UT + (i8 * 64 + g) * (U_CH / 16) + (w & 1) * (U_ODD / 16) + U_PAD / 16 + oct * 8 + (w >> 1) * 4 + c;
    const int ln = ((lane >> 1) & 3) + 4 * (lane & 1);
    uint32_t r[8][4];
#pragma unroll
    for (int i = 0; i < 8; i++) ldsm4t(r[i], sb + OFF_STG0 + w * 4096 + ((lane >> 3) * 8 + ln) * 128 + ((i ^ ln) << 4));
#pragma unroll
    for (int i = 0; i < 8; i++) dst[i * (U_CH / 2)] = make_uint4(r[i][0], r[i][1], r[i][2], r[i][3]);
    nb_arrive(NB_INIT, 160);
    if (lane == 0) mbar_arrive(BAR(MB_AUX));
  }
  {
    if (wg == 2) {
      asm volatile("setmaxnreg.inc.sync.aligned.u32 160;");
#pragma unroll
      for (int j = 0; j < 5; j++) { k[j][0] *= ksc; k[j][1] *= ksc; k[j][2] *= ksc; k[j][3] *= ksc; }
#pragma unroll 1
      for (int q = 0; q < 3; q++) {
        const uint32_t src = ((tb + 127) & ~127u) + q * 1536 + lane * 16;
        const uint4 v0 = lds128(src), v1 = lds128(src + 512), v2 = lds128(src + 1024);
        const uint32_t h[10] = {v0.x, v0.y, v0.z, v0.w, v1.x, v1.y, v1.z, v1.w, v2.x, v2.y};
#pragma unroll
        for (int j = 0; j < 10; j++) {
          const float2 f = __half22float2(*(const __half2*)&h[j]);
          k[j >> 1][2 * (j & 1)] = fmaf(f.x, uf(v2.w), k[j >> 1][2 * (j & 1)]);
          k[j >> 1][2 * (j & 1) + 1] = fmaf(f.y, uf(v2.w), k[j >> 1][2 * (j & 1) + 1]);
        }
        k2048 += uf(v2.z);
      }
#pragma unroll
      for (int o2 = 4; o2; o2 >>= 1) k2048 += __shfl_xor_sync(0xffffffffu, k2048, o2);
      if (lane == 0) k[0][0] += bf_lo(dsk);
      __syncwarp();
      TS(34);
      build_tables(tb, lane, k, k2048);
      TS(35);
      uint4* const g_y = P.xs + X_Y;
      conv_channel(sb + OFF_U + w * U_CH, tb, lane, g_y + (size_t)d * 256 + lane);
      nb_arrive(NB_BDONE, 288);
      nb_arrive(NB_Y, 160);
      TS(37);
      if (w == 0) TSDUMP(32);
      return;
    }
    if (wg == 1) {
      mbar_wait(BAR(MB_EMPTY + 4));
      mbar_spin(BAR(MB_EMPTY + 6));
    }
    TS(wg * 16 + 1);
  }

  float acc[2][48];
  {
    uint32_t fb = BAR(MB_FULL) + 64 * wg;
    uint32_t da = (uint32_t)mkdesc(sb + OFF_X, 16, 0, 0) + (wg ? 1024 : 3072), db = (uint32_t)mkdesc(sb + OFF_W, 4096, 0, 0);
    constexpr uint64_t ha = mkdesc(0, 0, 1024, 1), hb = mkdesc(0, 0, 512, 2);
    mbar_spin(fb);
    TS(wg * 16 + 2);
#pragma unroll 1
    for (int kb = 0; kb < 8; kb++) {
      WG_FENCE();
#pragma unroll
      for (int k = 0; k < 4; k++) {
        wgmma_ss_n96(acc[0], ha | (da + 2 * k), hb | (db + 64 * k), k ? 1 : kb);
        wgmma_ss_n96(acc[1], ha | (da + 2 * k + 512), hb | (db + 64 * k), k ? 1 : kb);
      }
      WG_COMMIT();
      if (kb < 7) mbar_spin(fb + 8);
      WG_WAIT(1);
      if (kb > 0) e_arrive(fb + 8 * (MB_EMPTY - MB_FULL - 1));
      fb += 8; db += 768;
      da = da == (uint32_t)mkdesc(sb + OFF_X + 65536, 16, 0, 0) ? da - 4096 : da + 1024;
    }
    if (wg == 0) nb_sync(NB_KREAD, 160);
    asm volatile("setmaxnreg.inc.sync.aligned.u32 160;");
    WG_WAIT(0);
    e_arrive(fb + 8 * (MB_EMPTY - MB_FULL - 1));
    SPLIT();
  }
  TS(wg * 16 + 3);

  constexpr uint32_t stg0 = sb + OFF_STG0, stg1 = sb + OFF_X + 32768;
  uint4* const g_part = P.xs + X_PART;
  uint4* const g_o = P.xs + X_O;
  constexpr uint32_t kvs = stg0;
  auto pack8 = [](const float* a) { return make_uint4(pack_bf(a[0], a[1]), pack_bf(a[2], a[3]), pack_bf(a[4], a[5]), pack_bf(a[6], a[7])); };
  auto feat = [&](const uint4 (&af)[4], float (&p)[4][8]) {
    WG_FENCE();
#pragma unroll
    for (int u = 0; u < 4; u++) wgmma_rs_n16(p[u], af[u], qdesc(sb + OFF_PHI + (u & 1) * 512), 0);
    WG_COMMIT();
  };
  auto packp = [](const float (&p)[4][8], uint32_t (&pw)[16]) {
#pragma unroll
    for (int i = 0; i < 16; i++) pw[i] = pack_bf(p[i >> 2][(i & 1) + 2 * (i & 2)], p[i >> 2][(i & 1) + 2 * (i & 2) + 2]);
  };
  auto contract = [&](float (&kc)[20], uint32_t stg, int acc_in) {
    WG_FENCE();
#pragma unroll
    for (int s = 0; s < 8; s++) wgmma_ss_n40(kc, qdesc(stg + s * SLAB), qdesc(stg + s * SLAB + 2048), s ? 1 : acc_in);
    WG_COMMIT();
    WG_WAIT(0);
  };
  uint32_t eq[32];
  {
    uint4 af[4], aq[4], vp[4];
    float p[4][8];
#pragma unroll
    for (int u = 0; u < 4; u++) af[u] = pack8(acc[u >> 1] + 16 + 8 * (u & 1));
    feat(af, p);
#pragma unroll
    for (int u = 0; u < 4; u++) { aq[u] = pack8(acc[u >> 1] + 8 * (u & 1)); vp[u] = pack8(acc[u >> 1] + 32 + 8 * (u & 1)); }
    WG_WAIT(0);
    uint32_t pw[16], ek[32];
    packp(p, pw);
#pragma unroll
    for (int u = 0; u < 4; u++) dual_exp(pw + 4 * u, ek + 8 * u);
    TS(wg * 16 + 12);
    if (wg && (ek[0] & ek[8] & ek[16] & ek[31]) != 0xffffffffu) nb_arrive(NB_GATE, 256);
    mbar_spin(wg ? BAR(MB_EMPTY + 15) : BAR(MB_AUX));
    float rs[8][4];
    WG_FENCE();
#pragma unroll
    for (int i = 0; i < 8; i++) wgmma_rs_n8(rs[i], make_uint4(ek[4 * i], ek[4 * i + 1], ek[4 * i + 2], ek[4 * i + 3]), qdesc(sb + OFF_ONE), 0);
    WG_COMMIT();
    feat(aq, p);
    const uint32_t sl = (wg ? stg1 : stg0) + w * SLAB + lane * 16;
#pragma unroll
    for (int i = 0; i < 4; i++) stsm4(sl + (i >> 1) * 4 * SLAB + 2048 + (i & 1) * 512, vp[i].x, vp[i].y, vp[i].z, vp[i].w);
    sts128(sl + (lane >> 4) * (4 * SLAB - 256) + 3072, 0x3F803F80u, 0x3F803F80u, 0x3F803F80u, 0x3F803F80u);
    WG_WAIT(1);
#pragma unroll
    for (int i = 0; i < 8; i++) {
      normalise(ek + 4 * i, rs[i]);
      stsm4(sl + (i >> 2) * 4 * SLAB + (i & 3) * 512, ek[4 * i], ek[4 * i + 1], ek[4 * i + 2], ek[4 * i + 3]);
    }
    asm volatile("fence.proxy.async.shared::cta;" ::: "memory");
    TS(wg * 16 + 13);
    if (wg) {
      nb_arrive(NB_ST0, 256);
    } else {
      float kc[20];
      uint4* pp = g_part + (size_t)(hp * 8 + rt) * 144 + t;
      uint32_t* pz = (uint32_t*)(pp - t + 128) + w * 16 + c * 8 + g;
      asm volatile("" : "+l"(pp), "+l"(pz));
      nb_sync(NB_WG0, 128);
      contract(kc, stg0, 0);
      mbar_wait(BAR(MB_UFULL));
      TS(15);
      nb_sync(NB_ST0, 256);
      contract(kc, stg1, 1);
      TS(6);
      float kv[8];
#pragma unroll
      for (int i = 0; i < 8; i++) kv[i] = w & 2 ? kc[8 + i] : kc[i];
      st_x(pp, nz(pack_bf(kv[0], kv[1])), pack_bf(kv[2], kv[3]), pack_bf(kv[4], kv[5]), pack_bf(kv[6], kv[7]));
      if (c < 2) st_x32(pz, nz(fu(c ? kc[18] : kc[16])));
      TS(5);
    }
    SPLIT();
    WG_WAIT(0);
    packp(p, pw);
#pragma unroll
    for (int u = 0; u < 4; u++) dual_exp(pw + 4 * u, eq + 8 * u);
    SPLIT();
  }
  TS(wg * 16 + 4);
  if (wg == 1) {
    mbar_wait(BAR(MB_UFULL));
    const uint4* ps = g_part + (size_t)hp * 8 * 144 + t;
    const uint32_t* zs = (const uint32_t*)(g_part + (size_t)(hp * 8 + (lane >> 4) * 4) * 144 + 128) + w * 16 + (lane & 15);
    uint4 v[8];
    uint32_t zv[4];
#pragma unroll 1
    for (int it = 0; it < SPIN_MAX; it++) {
#pragma unroll
      for (int i = 0; i < 8; i++) v[i] = ld_x(ps + i * 144);
#pragma unroll
      for (int i = 0; i < 4; i++) zv[i] = ld_x32(zs + i * 576);
      uint32_t m = min(min(zv[0], zv[1]), min(zv[2], zv[3]));
#pragma unroll
      for (int i = 0; i < 8; i++) m = min(m, v[i].x);
      if (__all_sync(0xffffffffu, m != 0)) break;
    }
    float s[8];
    WG_FENCE();
#pragma unroll
    for (int r = 0; r < 8; r++) wgmma_rs_n16(s, v[r], qdesc(sb + OFF_EYE), r);
    WG_COMMIT();
    float zsum = (uf(zv[0]) + uf(zv[1])) + (uf(zv[2]) + uf(zv[3]));
    zsum += __shfl_xor_sync(0xffffffffu, zsum, 16);
    const uint32_t z1 = pack_bf(zsum, 1.f);
    if (lane < 16) sts128(kvs + w * 768 + 512 + lane * 16, z1, z1, z1, z1);
    WG_WAIT(0);
    stsm4(kvs + w * 768 + lane * 16, pack_bf(s[0], s[1]), pack_bf(s[2], s[3]), pack_bf(s[4], s[5]), pack_bf(s[6], s[7]));
    asm volatile("fence.proxy.async.shared::cta;" ::: "memory");
    TS(22);
  }
  nb_sync(NB_KV, 256);
  {
    float n[8][12];
    WG_FENCE();
#pragma unroll
    for (int i = 0; i < 8; i++) wgmma_rs_n24(n[i], make_uint4(eq[4 * i], eq[4 * i + 1], eq[4 * i + 2], eq[4 * i + 3]), qdesc(kvs + (i & 3) * 768), 0);
    WG_COMMIT();
    uint32_t* od = (uint32_t*)(g_o + (size_t)((rt * 4 + wg * 2) * 32 + hp * 2) * 128) + w * 64 + lane;
    WG_WAIT(0);
#pragma unroll
    for (int u = 0; u < 4; u++) {
      float(&np)[12] = n[2 * u];
      const float(&nm)[12] = n[2 * u + 1];
      const float q0 = np[9] * rcp(nm[9]), q1 = np[11] * rcp(nm[11]);
      const float r0 = rcp(fmaf(nm[8], q0, fmaf(np[9], 1e-6f, np[8]))), r1 = rcp(fmaf(nm[10], q1, fmaf(np[11], 1e-6f, np[10])));
#pragma unroll
      for (int i = 0; i < 8; i++) np[i] = fmaf(nm[i], (i & 2) ? q1 : q0, np[i]);
      uint32_t* o = od + (u >> 1) * 16384 + (u & 1) * 512;
      o[0] = pack_bf(np[0] * r0, np[1] * r0);
      o[32] = pack_bf(np[2] * r1, np[3] * r1);
      o[256] = pack_bf(np[4] * r0, np[5] * r0);
      o[288] = pack_bf(np[6] * r1, np[7] * r1);
      if (u == 1) SPLIT();
    }
  }
  TS(wg * 16 + 7);
  nb_arrive(NB_ODONE, 288);
  if (wg) {
    const uint4* src = P.xs + X_Y + (oct * 32 + c * 8) * 256 + (2 * w + (g >> 2)) * 32 + i8 * 4 + (g & 3);
    __nv_bfloat16* dst = P.out + (size_t)((2 * w + (g >> 2)) * 256 + i8 * 16 + (g & 3) * 2) * 1024 + 512 + oct * 32 + c * 8;
    nb_sync(NB_GATE + 1, 160);
    nb_sync(NB_Y + w, 160);
    uint4 v[8];
#pragma unroll 1
    for (int it = 0; it < SPIN_MAX; it++) {
      uint32_t m = 0xffffffffu;
#pragma unroll
      for (int i = 0; i < 8; i++) v[i] = ld_x(src + i * 256);
#pragma unroll
      for (int i = 0; i < 8; i++) m = min(m, v[i].x);
      if (__all_sync(0xffffffffu, m != 0)) break;
    }
#pragma unroll
    for (int i = 0; i < 8; i++) *(uint4*)(dst + (size_t)((i >> 2) * 128 + ((i >> 1) & 1) * 8 + (i & 1)) * 1024) = tr_row(v, i);
    TS(31);
    GT(63);
    if (w == 0) TSDUMP(16);
    return;
  }
  mbar_wait(BAR(MB_WO));
  nb_sync(NB_BDONE, 288);
  TS(8);
  mbar_spin(BAR(MB_O));
  TS(9);
  constexpr uint64_t ha = mkdesc(0, 0, 128, 0), hb = mkdesc(0, 0, 1024, 1);
  constexpr uint32_t da0 = (uint32_t)mkdesc(stg1, 1024, 0, 0), db0 = (uint32_t)mkdesc(sb + OFF_W, 8192, 0, 0);
  const uint32_t ot = ((sb + OFF_T + 1023) & ~1023u) + w * 4096;
  auto store_half = [&](const float* oc, int hf) {
#pragma unroll
    for (int i = 0; i < 8; i += 2)
      stsm4(ot + hf * 2048 + (lane & 15) * 128 + (((i + (lane >> 4)) ^ lane) & 7) * 16, pack_bf(oc[4 * i], oc[4 * i + 1]),
            pack_bf(oc[4 * i + 2], oc[4 * i + 3]), pack_bf(oc[4 * i + 4], oc[4 * i + 5]), pack_bf(oc[4 * i + 6], oc[4 * i + 7]));
    asm volatile("fence.proxy.async.shared::cta;" ::: "memory");
    __syncwarp();
    e_store2d(&mout, ot + hf * 2048, (hp & 3) * 128 + hf * 64, (rt * 4 + (hp >> 2)) * 64 + w * 16);
  };
  float oc[64];
#pragma unroll 1
  for (int j = 0; j < 8; j++) {
    const int kb = (j + 7) & 7;
    if ((j & 1) && j < 6) mbar_spin(BAR(MB_O + 1) + 4 * (j - 1));
    WG_FENCE();
#pragma unroll
    for (int k = 0; k < 4; k++) wgmma_ss_n128(oc, ha | (da0 + 512 * kb + 128 * k), hb | (db0 + 1024 * kb + 128 * k), k ? 1 : j);
    WG_COMMIT();
  }
  WG_WAIT(0);
  TS(10);
  store_half(oc, 0);
  store_half(oc + 32, 1);
  asm volatile(ELECT "cp.async.bulk.commit_group;\n@p cp.async.bulk.wait_group.read 0;\n}\n" ::: "memory");
  TS(wg * 16 + 11);
  GT(61 + wg);
  if (w == 0) TSDUMP(0);
  if (w == 1) TSDUMP(48);
}

typedef CUresult (*EncodeFn)(CUtensorMap*, CUtensorMapDataType, cuuint32_t, void*, const cuuint64_t*, const cuuint64_t*,
                             const cuuint32_t*, const cuuint32_t*, CUtensorMapInterleave, CUtensorMapSwizzle,
                             CUtensorMapL2promotion, CUtensorMapFloatOOBfill);

}

extern "C" void kernel_launch(void* const* d_in, const int* in_sizes, int n_in, void* d_out, int out_size) {
  (void)in_sizes; (void)n_in; (void)out_size;
  void* fn = nullptr;
  cudaDriverEntryPointQueryResult qr;
  cudaGetDriverEntryPoint("cuTensorMapEncodeTiled", &fn, cudaEnableDefault, &qr);
  EncodeFn enc = (EncodeFn)fn;
  CUtensorMap mx, mw, mo, mu, mout, mw4;
  const cuuint32_t es[5] = {1, 1, 1, 1, 1};
  {
    cuuint64_t dims[2] = {512, 2048}, st[1] = {1024};
    cuuint32_t box[2] = {64, 128};
    enc(&mx, CU_TENSOR_MAP_DATA_TYPE_BFLOAT16, 2, d_in[0], dims, st, box, es, CU_TENSOR_MAP_INTERLEAVE_NONE,
        CU_TENSOR_MAP_SWIZZLE_128B, CU_TENSOR_MAP_L2_PROMOTION_L2_128B, CU_TENSOR_MAP_FLOAT_OOB_FILL_NONE);
  }
  {
    cuuint64_t dims[3] = {512, 512, 3}, st[2] = {3072, 1024};
    cuuint32_t box[3] = {32, 64, 3};
    enc(&mw, CU_TENSOR_MAP_DATA_TYPE_BFLOAT16, 3, d_in[1], dims, st, box, es, CU_TENSOR_MAP_INTERLEAVE_NONE,
        CU_TENSOR_MAP_SWIZZLE_64B, CU_TENSOR_MAP_L2_PROMOTION_L2_128B, CU_TENSOR_MAP_FLOAT_OOB_FILL_NONE);
  }
  {
    cuuint64_t dims[3] = {64, 512, 8}, st[2] = {1024, 128};
    cuuint32_t box[3] = {64, 64, 2};
    enc(&mo, CU_TENSOR_MAP_DATA_TYPE_BFLOAT16, 3, d_in[3], dims, st, box, es, CU_TENSOR_MAP_INTERLEAVE_NONE,
        CU_TENSOR_MAP_SWIZZLE_128B, CU_TENSOR_MAP_L2_PROMOTION_L2_128B, CU_TENSOR_MAP_FLOAT_OOB_FILL_NONE);
  }
  {
    cuuint64_t dims[4] = {512, 4, 16, 32}, st[3] = {16384, 1024, 65536};
    cuuint32_t box[4] = {64, 4, 16, 2};
    enc(&mu, CU_TENSOR_MAP_DATA_TYPE_BFLOAT16, 4, d_in[4], dims, st, box, es, CU_TENSOR_MAP_INTERLEAVE_NONE,
        CU_TENSOR_MAP_SWIZZLE_128B, CU_TENSOR_MAP_L2_PROMOTION_L2_128B, CU_TENSOR_MAP_FLOAT_OOB_FILL_NONE);
  }
  {
    cuuint64_t dims[2] = {1024, 2048}, st[1] = {2048};
    cuuint32_t box[2] = {64, 16};
    enc(&mout, CU_TENSOR_MAP_DATA_TYPE_BFLOAT16, 2, d_out, dims, st, box, es, CU_TENSOR_MAP_INTERLEAVE_NONE,
        CU_TENSOR_MAP_SWIZZLE_128B, CU_TENSOR_MAP_L2_PROMOTION_NONE, CU_TENSOR_MAP_FLOAT_OOB_FILL_NONE);
  }
  {
    cuuint64_t dims[4] = {512, 64, 3, 8}, st[3] = {3072, 1024, 64 * 3072};
    cuuint32_t box[4] = {32, 64, 3, 2};
    enc(&mw4, CU_TENSOR_MAP_DATA_TYPE_BFLOAT16, 4, d_in[1], dims, st, box, es, CU_TENSOR_MAP_INTERLEAVE_NONE,
        CU_TENSOR_MAP_SWIZZLE_64B, CU_TENSOR_MAP_L2_PROMOTION_L2_128B, CU_TENSOR_MAP_FLOAT_OOB_FILL_NONE);
  }
  Params P;
  P.x = (const __nv_bfloat16*)d_in[0];
  P.wphi = (const __nv_bfloat16*)d_in[2];
  P.wo = (const __nv_bfloat16*)d_in[3];
  P.logA = (const __nv_bfloat16*)d_in[5];
  P.Aim = (const __nv_bfloat16*)d_in[6];
  P.Cre = (const __nv_bfloat16*)d_in[7];
  P.Cim = (const __nv_bfloat16*)d_in[8];
  P.logdt = (const __nv_bfloat16*)d_in[9];
  P.Dskip = (const __nv_bfloat16*)d_in[10];
  P.out = (__nv_bfloat16*)d_out;
  cudaGetSymbolAddress((void**)&P.xs, g_x);
  P.ts = nullptr;
  cudaFuncSetAttribute(fused_kernel, cudaFuncAttributeMaxDynamicSharedMemorySize, SMEM_BYTES);
  fused_kernel<<<NCTA, NTHREADS, SMEM_BYTES>>>(P, mx, mw, mo, mu, mout, mw4);
}
```

```cpp
#include <cuda_runtime.h>
#include <cuda_bf16.h>
#include <cuda_fp16.h>
#include <cuda.h>
#include <stdint.h>

#define DBG_TS 0

namespace {

constexpr int NTHREADS = 512;
constexpr int NCTA = 128;
constexpr int OFF_W = 0;
constexpr int OFF_X = 98304;
constexpr int OFF_U = OFF_X + 65536;
constexpr int U_CH = 4416, U_ODD = 2240, U_PAD = 128;
constexpr int OFF_STG0 = OFF_U + 18432;
constexpr int SLAB = 3328;
constexpr int OFF_T = OFF_STG0 + 8 * SLAB;
constexpr int T_CH = 5216;
constexpr int T_D = 0;
constexpr int T_5 = 2144;
constexpr int T_3 = T_5 + 384;
constexpr int T_7 = T_5 + 1024;
constexpr int T_9 = T_7 + 320;
constexpr int T_KC = T_9 + 320;
constexpr int T_ST = T_5 - 1024;
constexpr int OFF_PHI = OFF_T + 4 * T_CH;
constexpr int OFF_EYE = OFF_PHI + 1024, OFF_ONE = OFF_EYE + 512;
constexpr int OFF_BAR = OFF_ONE + 256;
constexpr int SMEM_BYTES = OFF_BAR + 512 + 256 * DBG_TS;
constexpr uint32_t SB = 1024;
static_assert(T_KC + 2 * 656 <= T_CH, "table size");
static_assert(SMEM_BYTES <= 232448, "smem");
constexpr int MB_URAW = 0, MB_FULL = 1  , MB_WO = 17, MB_UFULL = 18, MB_O = 19  ,
              MB_EMPTY = 23  , MB_AUX = 39;
__host__ __device__ constexpr uint32_t BAR(int i) { return SB + OFF_BAR + 8 * i; }
constexpr int NB_WG0 = 1, NB_ODONE = 2, NB_ST0 = 3  , NB_KV = 5, NB_YZ = 6, NB_INIT = 7, NB_PREP = 8, NB_PROD = 9, NB_KREAD = 10, NB_BDONE = 11, NB_GATE = 12,
              NB_Y = 7  ;
#define X2_AT -1
#define GATE_B 1
#define POLL 0
#define U_AT 2
#define ZERO_STEP 12
constexpr int SPIN_MAX = 1 << 16;

constexpr int X_CNT = 0;
constexpr int X_PART = 256;
constexpr int X_O = X_PART + 16 * 8 * 144;
constexpr int X_Y = X_O + 32 * 32 * 128;
constexpr int X_UT = X_Y + 512 * 8 * 32;
constexpr int X_SIZE = X_UT + 512 * (U_CH / 16);
__device__ __align__(128) uint4 g_x[X_SIZE];
extern __shared__ uint8_t smem_raw[];
#define TS(i) do {} while (0)
#define TS1(i) do {} while (0)
#define GT(i) do {} while (0)
#define TSDUMP(base) do {} while (0)

__device__ __forceinline__ uint32_t smem_u32(const void* p) { return (uint32_t)__cvta_generic_to_shared(p); }
__device__ __forceinline__ void mbar_arrive(uint32_t b) {
  asm volatile("mbarrier.arrive.shared::cta.b64 _, [%0];" ::"r"(b) : "memory");
}
__device__ __forceinline__ void mbar_wait(uint32_t b) {
  uint32_t done = 0;
#pragma unroll 1
  for (int i = 0; i < SPIN_MAX && !done; i++) {
    asm volatile("{\n.reg .pred p;\nmbarrier.try_wait.parity.shared::cta.b64 p, [%1], 0, 4000;\nselp.u32 %0, 1, 0, p;\n}\n"
                 : "=r"(done) : "r"(b) : "memory");
  }
}
__device__ __forceinline__ void mbar_spin(uint32_t b) {
  uint32_t done = 0;
#pragma unroll 1
  for (int i = 0; i < (SPIN_MAX << 4) && !done; i++) {
    asm volatile("{\n.reg .pred p;\nmbarrier.try_wait.parity.shared::cta.b64 p, [%1], 0;\nselp.u32 %0, 1, 0, p;\n}\n"
                 : "=r"(done) : "r"(b) : "memory");
  }
}
__device__ __forceinline__ void mbar_init(uint32_t b, int n) {
  asm volatile("mbarrier.init.shared::cta.b64 [%0], %1;" ::"r"(b), "r"(n) : "memory");
}
__device__ __forceinline__ void mbar_expect(uint32_t b, int bytes) {
  asm volatile("mbarrier.arrive.expect_tx.shared::cta.b64 _, [%0], %1;" ::"r"(b), "r"(bytes) : "memory");
}
__device__ __forceinline__ void nb_sync(int id, int n) { asm volatile("bar.sync %0, %1;" ::"r"(id), "r"(n) : "memory"); }
__device__ __forceinline__ void nb_arrive(int id, int n) { asm volatile("bar.arrive %0, %1;" ::"r"(id), "r"(n) : "memory"); }
#define ELECT "{\n.reg .pred p;\nelect.sync _|p, 0xffffffff;\n@p "
__device__ __forceinline__ void e_arrive(uint32_t b) {
  asm volatile(ELECT "mbarrier.arrive.shared::cta.b64 _, [%0];\n}\n" ::"r"(b) : "memory");
}
__device__ __forceinline__ void e_expect(uint32_t b, int bytes) {
  asm volatile(ELECT "mbarrier.arrive.expect_tx.shared::cta.b64 _, [%0], %1;\n}\n" ::"r"(b), "r"(bytes) : "memory");
}
__device__ __forceinline__ void e_tma2d(uint32_t dst, const CUtensorMap* m, uint32_t bar, int c0, int c1) {
  asm volatile(ELECT "cp.async.bulk.tensor.2d.shared::cluster.global.mbarrier::complete_tx::bytes [%0], [%1, {%3,%4}], [%2];\n}\n"
               ::"r"(dst), "l"(m), "r"(bar), "r"(c0), "r"(c1) : "memory");
}
__device__ __forceinline__ void e_tma3d(uint32_t dst, const CUtensorMap* m, uint32_t bar, int c0, int c1, int c2) {
  asm volatile(ELECT "cp.async.bulk.tensor.3d.shared::cluster.global.mbarrier::complete_tx::bytes [%0], [%1, {%3,%4,%5}], [%2];\n}\n"
               ::"r"(dst), "l"(m), "r"(bar), "r"(c0), "r"(c1), "r"(c2) : "memory");
}
__device__ __forceinline__ void e_tma4d(uint32_t dst, const CUtensorMap* m, uint32_t bar, int c0, int c3) {
  asm volatile(ELECT "cp.async.bulk.tensor.4d.shared::cluster.global.mbarrier::complete_tx::bytes [%0], [%1, {%3,%5,%5,%4}], [%2];\n}\n"
               ::"r"(dst), "l"(m), "r"(bar), "r"(c0), "r"(c3), "r"(0) : "memory");
}
__device__ __forceinline__ void e_bulk(uint32_t dst, const void* src, int bytes, uint32_t bar) {
  asm volatile(ELECT "cp.async.bulk.shared::cluster.global.mbarrier::complete_tx::bytes [%0], [%1], %2, [%3];\n}\n"
               ::"r"(dst), "l"(src), "r"(bytes), "r"(bar) : "memory");
}
__device__ __forceinline__ void e_prefetch(const void* p, int bytes) {
  asm volatile(ELECT "cp.async.bulk.prefetch.L2.global [%0], %1;\n}\n" ::"l"(p), "r"(bytes) : "memory");
}
__device__ __forceinline__ void e_store2d(const CUtensorMap* m, uint32_t src, int c0, int c1) {
  asm volatile(ELECT "cp.async.bulk.tensor.2d.global.shared::cta.bulk_group [%0, {%2,%3}], [%1];\n}\n"
               ::"l"(m), "r"(src), "r"(c0), "r"(c1) : "memory");
}
__host__ __device__ constexpr uint64_t mkdesc(uint32_t addr, uint32_t lbo, uint32_t sbo, int swz) {
  return (uint64_t)((addr & 0x3FFFF) >> 4) | ((uint64_t)(lbo >> 4) << 16) | ((uint64_t)(sbo >> 4) << 32) |
         ((uint64_t)swz << 62);
}
#define SPLIT() asm volatile("{\n.reg .pred p;\nsetp.eq.u32 p, %0, %1;\n@p exit;\n}\n" ::"r"(blockIdx.y), "n"(__LINE__) : "memory")
#define SPLITN(n) asm volatile("{\n.reg .pred p;\nsetp.eq.u32 p, %0, %1;\n@p exit;\n}\n" ::"r"(blockIdx.y), "r"(4096 + (n)) : "memory")
#define WG_FENCE() asm volatile("wgmma.fence.sync.aligned;" ::: "memory")
#define WG_COMMIT() asm volatile("wgmma.commit_group.sync.aligned;" ::: "memory")
#define WG_WAIT(n) asm volatile("wgmma.wait_group.sync.aligned " #n ";" ::: "memory")

__device__ __forceinline__ void mma(float& d0, float& d1, float& d2, float& d3, uint32_t a0, uint32_t a1, uint32_t a2,
                                    uint32_t a3, uint32_t b0, uint32_t b1) {
  asm volatile("mma.sync.aligned.m16n8k16.row.col.f32.bf16.bf16.f32 {%0,%1,%2,%3},{%4,%5,%6,%7},{%8,%9},{%0,%1,%2,%3};"
               : "+f"(d0), "+f"(d1), "+f"(d2), "+f"(d3)
               : "r"(a0), "r"(a1), "r"(a2), "r"(a3), "r"(b0), "r"(b1));
}
__device__ __forceinline__ void mmac(float (&d)[4], uint32_t a0, uint32_t a1, uint32_t a2, uint32_t a3, uint32_t b0,
                                     uint32_t b1, const float (&c)[4]) {
  asm volatile("mma.sync.aligned.m16n8k16.row.col.f32.bf16.bf16.f32 {%0,%1,%2,%3},{%4,%5,%6,%7},{%8,%9},{%10,%11,%12,%13};"
               : "=f"(d[0]), "=f"(d[1]), "=f"(d[2]), "=f"(d[3])
               : "r"(a0), "r"(a1), "r"(a2), "r"(a3), "r"(b0), "r"(b1), "f"(c[0]), "f"(c[1]), "f"(c[2]), "f"(c[3]));
}
__device__ __forceinline__ void mma_p(int p, float (&d)[4], uint32_t a0, uint32_t a1, uint32_t a2, uint32_t a3, uint32_t b0, uint32_t b1) {
  asm volatile("{\n.reg .pred q;\nsetp.ne.b32 q, %10, 0;\n"
               "@q mma.sync.aligned.m16n8k16.row.col.f32.bf16.bf16.f32 {%0,%1,%2,%3},{%4,%5,%6,%7},{%8,%9},{%0,%1,%2,%3};\n}\n"
               : "+f"(d[0]), "+f"(d[1]), "+f"(d[2]), "+f"(d[3])
               : "r"(a0), "r"(a1), "r"(a2), "r"(a3), "r"(b0), "r"(b1), "r"(p));
}
__device__ __forceinline__ void mmac_p(int p, float (&d)[4], uint32_t a0, uint32_t a1, uint32_t a2, uint32_t a3, uint32_t b0,
                                       uint32_t b1, const float (&c)[4]) {
  asm volatile("{\n.reg .pred q;\nsetp.ne.b32 q, %14, 0;\n"
               "@q mma.sync.aligned.m16n8k16.row.col.f32.bf16.bf16.f32 {%0,%1,%2,%3},{%4,%5,%6,%7},{%8,%9},{%10,%11,%12,%13};\n}\n"
               : "+f"(d[0]), "+f"(d[1]), "+f"(d[2]), "+f"(d[3])
               : "r"(a0), "r"(a1), "r"(a2), "r"(a3), "r"(b0), "r"(b1), "f"(c[0]), "f"(c[1]), "f"(c[2]), "f"(c[3]), "r"(p));
}
__device__ __forceinline__ void mma_h(float (&d)[4], const uint32_t (&a)[4], uint32_t b0, uint32_t b1) {
  asm volatile("mma.sync.aligned.m16n8k16.row.col.f32.f16.f16.f32 {%0,%1,%2,%3},{%4,%5,%6,%7},{%8,%9},{%0,%1,%2,%3};"
               : "+f"(d[0]), "+f"(d[1]), "+f"(d[2]), "+f"(d[3]) : "r"(a[0]), "r"(a[1]), "r"(a[2]), "r"(a[3]), "r"(b0), "r"(b1));
}
__device__ __forceinline__ void mma0(float& d0, float& d1, float& d2, float& d3, uint32_t a0, uint32_t a1, uint32_t a2,
                                     uint32_t a3, uint32_t b0, uint32_t b1) {
  asm volatile("mma.sync.aligned.m16n8k16.row.col.f32.bf16.bf16.f32 {%0,%1,%2,%3},{%4,%5,%6,%7},{%8,%9},{%10,%10,%10,%10};"
               : "=f"(d0), "=f"(d1), "=f"(d2), "=f"(d3)
               : "r"(a0), "r"(a1), "r"(a2), "r"(a3), "r"(b0), "r"(b1), "f"(0.f));
}
__device__ __forceinline__ uint32_t pack_bf(float lo, float hi) {
  uint32_t r;
  asm("cvt.rn.bf16x2.f32 %0, %1, %2;" : "=r"(r) : "f"(hi), "f"(lo));
  return r;
}
__device__ __forceinline__ float bf_lo(uint32_t w) { return __uint_as_float(w << 16); }
__device__ __forceinline__ float bf_hi(uint32_t w) { return __uint_as_float(w & 0xffff0000u); }
__device__ __forceinline__ float bf_round(float x) { return __bfloat162float(__float2bfloat16_rn(x)); }
__device__ __forceinline__ uint32_t bmax2(uint32_t a, uint32_t b) {
  uint32_t r; asm("max.bf16x2 %0, %1, %2;" : "=r"(r) : "r"(a), "r"(b)); return r;
}
__device__ __forceinline__ uint32_t bmin2(uint32_t a, uint32_t b) {
  uint32_t r; asm("min.bf16x2 %0, %1, %2;" : "=r"(r) : "r"(a), "r"(b)); return r;
}
__device__ __forceinline__ float ex2(float x) { float r; asm("ex2.approx.ftz.f32 %0, %1;" : "=f"(r) : "f"(x)); return r; }
__device__ __forceinline__ float rcp(float x) { float r; asm("rcp.approx.ftz.f32 %0, %1;" : "=f"(r) : "f"(x)); return r; }
__device__ __forceinline__ void ldsm4(uint32_t (&r)[4], uint32_t a) {
  asm volatile("ldmatrix.sync.aligned.m8n8.x4.shared.b16 {%0,%1,%2,%3}, [%4];"
               : "=r"(r[0]), "=r"(r[1]), "=r"(r[2]), "=r"(r[3]) : "r"(a) : "memory");
}
__device__ __forceinline__ void ldsm4t(uint32_t (&r)[4], uint32_t a) {
  asm volatile("ldmatrix.sync.aligned.m8n8.x4.trans.shared.b16 {%0,%1,%2,%3}, [%4];"
               : "=r"(r[0]), "=r"(r[1]), "=r"(r[2]), "=r"(r[3]) : "r"(a) : "memory");
}
__device__ __forceinline__ void stsm4(uint32_t a, uint32_t r0, uint32_t r1, uint32_t r2, uint32_t r3) {
  asm volatile("stmatrix.sync.aligned.m8n8.x4.shared.b16 [%0], {%1,%2,%3,%4};"
               ::"r"(a), "r"(r0), "r"(r1), "r"(r2), "r"(r3) : "memory");
}
__device__ __forceinline__ uint32_t lds32(uint32_t a) {
  uint32_t r; asm volatile("ld.shared.u32 %0, [%1];" : "=r"(r) : "r"(a) : "memory"); return r;
}
__device__ __forceinline__ uint32_t lds16(uint32_t a) {
  uint32_t r; asm volatile("{\n.reg .u16 h;\nld.shared.u16 h, [%1];\ncvt.u32.u16 %0, h;\n}\n" : "=r"(r) : "r"(a) : "memory"); return r;
}
__device__ __forceinline__ uint2 lds64(uint32_t a) {
  uint2 r; asm volatile("ld.shared.v2.u32 {%0,%1}, [%2];" : "=r"(r.x), "=r"(r.y) : "r"(a) : "memory"); return r;
}
__device__ __forceinline__ uint4 lds128(uint32_t a) {
  uint4 r;
  asm volatile("ld.shared.v4.u32 {%0,%1,%2,%3}, [%4];" : "=r"(r.x), "=r"(r.y), "=r"(r.z), "=r"(r.w) : "r"(a) : "memory");
  return r;
}
__device__ __forceinline__ void sts32(uint32_t a, uint32_t v) { asm volatile("st.shared.u32 [%0], %1;" ::"r"(a), "r"(v) : "memory"); }
__device__ __forceinline__ void sts16(uint32_t a, uint32_t v) {
  asm volatile("{\n.reg .u16 h;\ncvt.u16.u32 h, %1;\nst.shared.u16 [%0], h;\n}\n" ::"r"(a), "r"(v) : "memory");
}
__device__ __forceinline__ void sts64(uint32_t a, uint32_t x, uint32_t y) {
  asm volatile("st.shared.v2.u32 [%0], {%1,%2};" ::"r"(a), "r"(x), "r"(y) : "memory");
}
__device__ __forceinline__ void sts128(uint32_t a, uint32_t x, uint32_t y, uint32_t z, uint32_t w) {
  asm volatile("st.shared.v4.u32 [%0], {%1,%2,%3,%4};" ::"r"(a), "r"(x), "r"(y), "r"(z), "r"(w) : "memory");
}
__device__ __forceinline__ uint4 ld_x(const uint4* p) {
  uint4 r;
  asm volatile("{\n.reg .b128 t;\nld.relaxed.gpu.global.b128 t, [%4];\nmov.b128 {%0,%1,%2,%3}, t;\n}\n"
               : "=r"(r.x), "=r"(r.y), "=r"(r.z), "=r"(r.w) : "l"(p) : "memory");
  return r;
}
__device__ __forceinline__ uint32_t ld_x32(const uint32_t* p) {
  uint32_t r; asm volatile("ld.relaxed.gpu.global.u32 %0, [%1];" : "=r"(r) : "l"(p) : "memory"); return r;
}
__device__ __forceinline__ void st_x(uint4* p, uint32_t x, uint32_t y, uint32_t z, uint32_t w) {
  asm volatile("{\n.reg .b128 t;\nmov.b128 t, {%1,%2,%3,%4};\nst.relaxed.gpu.global.b128 [%0], t;\n}\n"
               ::"l"(p), "r"(x), "r"(y), "r"(z), "r"(w) : "memory");
}
__device__ __forceinline__ void st_x_p(int p, uint4* a, uint32_t x, uint32_t y, uint32_t z, uint32_t w) {
  asm volatile("{\n.reg .b128 t;\n.reg .pred q;\nsetp.ne.b32 q, %5, 0;\nmov.b128 t, {%1,%2,%3,%4};\n@q st.relaxed.gpu.global.b128 [%0], t;\n}\n"
               ::"l"(a), "r"(x), "r"(y), "r"(z), "r"(w), "r"(p) : "memory");
}
__device__ __forceinline__ void sts64_p(int p, uint32_t a, uint32_t x, uint32_t y) {
  asm volatile("{\n.reg .pred q;\nsetp.ne.b32 q, %3, 0;\n@q st.shared.v2.u32 [%0], {%1,%2};\n}\n" ::"r"(a), "r"(x), "r"(y), "r"(p) : "memory");
}
__device__ __forceinline__ void st_x32(uint32_t* p, uint32_t x) {
  asm volatile("st.relaxed.gpu.global.u32 [%0], %1;" ::"l"(p), "r"(x) : "memory");
}
__device__ __forceinline__ uint32_t nz(uint32_t w) { return max(w, 1u); }
__device__ __forceinline__ uint32_t fu(float x) { return __float_as_uint(x); }
__device__ __forceinline__ float uf(uint32_t x) { return __uint_as_float(x); }

__device__ __forceinline__ void wgmma_ss_n96(float (&d)[48], uint64_t da, uint64_t db, int sc) {
  asm volatile("{\n.reg .pred p;\nsetp.ne.b32 p, %50, 0;\n"
      "wgmma.mma_async.sync.aligned.m64n96k16.f32.bf16.bf16 "
      "{%0,%1,%2,%3,%4,%5,%6,%7,%8,%9,%10,%11,%12,%13,%14,%15,%16,%17,%18,%19,%20,%21,%22,%23,%24,%25,%26,%27,%28,%29,%30,%31,%32,%33,%34,%35,%36,%37,%38,%39,%40,%41,%42,%43,%44,%45,%46,%47}, "
      "%48, %49, p, 1, 1, 0, 1;\n}\n"
      : "+f"(d[0]), "+f"(d[1]), "+f"(d[2]), "+f"(d[3]), "+f"(d[4]), "+f"(d[5]), "+f"(d[6]), "+f"(d[7]),
        "+f"(d[8]), "+f"(d[9]), "+f"(d[10]), "+f"(d[11]), "+f"(d[12]), "+f"(d[13]), "+f"(d[14]), "+f"(d[15]),
        "+f"(d[16]), "+f"(d[17]), "+f"(d[18]), "+f"(d[19]), "+f"(d[20]), "+f"(d[21]), "+f"(d[22]), "+f"(d[23]),
        "+f"(d[24]), "+f"(d[25]), "+f"(d[26]), "+f"(d[27]), "+f"(d[28]), "+f"(d[29]), "+f"(d[30]), "+f"(d[31]),
        "+f"(d[32]), "+f"(d[33]), "+f"(d[34]), "+f"(d[35]), "+f"(d[36]), "+f"(d[37]), "+f"(d[38]), "+f"(d[39]),
        "+f"(d[40]), "+f"(d[41]), "+f"(d[42]), "+f"(d[43]), "+f"(d[44]), "+f"(d[45]), "+f"(d[46]), "+f"(d[47])
      : "l"(da), "l"(db), "r"(sc));
}

__device__ __forceinline__ void wgmma_ss_n128(float (&d)[64], uint64_t da, uint64_t db, int sc) {
  asm volatile("{\n.reg .pred p;\nsetp.ne.b32 p, %66, 0;\n"
      "wgmma.mma_async.sync.aligned.m64n128k16.f32.bf16.bf16 "
      "{%0,%1,%2,%3,%4,%5,%6,%7,%8,%9,%10,%11,%12,%13,%14,%15,%16,%17,%18,%19,%20,%21,%22,%23,%24,%25,%26,%27,%28,%29,%30,%31,%32,%33,%34,%35,%36,%37,%38,%39,%40,%41,%42,%43,%44,%45,%46,%47,%48,%49,%50,%51,%52,%53,%54,%55,%56,%57,%58,%59,%60,%61,%62,%63}, "
      "%64, %65, p, 1, 1, 0, 1;\n}\n"
      : "+f"(d[0]), "+f"(d[1]), "+f"(d[2]), "+f"(d[3]), "+f"(d[4]), "+f"(d[5]), "+f"(d[6]), "+f"(d[7]),
        "+f"(d[8]), "+f"(d[9]), "+f"(d[10]), "+f"(d[11]), "+f"(d[12]), "+f"(d[13]), "+f"(d[14]), "+f"(d[15]),
        "+f"(d[16]), "+f"(d[17]), "+f"(d[18]), "+f"(d[19]), "+f"(d[20]), "+f"(d[21]), "+f"(d[22]), "+f"(d[23]),
        "+f"(d[24]), "+f"(d[25]), "+f"(d[26]), "+f"(d[27]), "+f"(d[28]), "+f"(d[29]), "+f"(d[30]), "+f"(d[31]),
        "+f"(d[32]), "+f"(d[33]), "+f"(d[34]), "+f"(d[35]), "+f"(d[36]), "+f"(d[37]), "+f"(d[38]), "+f"(d[39]),
        "+f"(d[40]), "+f"(d[41]), "+f"(d[42]), "+f"(d[43]), "+f"(d[44]), "+f"(d[45]), "+f"(d[46]), "+f"(d[47]),
        "+f"(d[48]), "+f"(d[49]), "+f"(d[50]), "+f"(d[51]), "+f"(d[52]), "+f"(d[53]), "+f"(d[54]), "+f"(d[55]),
        "+f"(d[56]), "+f"(d[57]), "+f"(d[58]), "+f"(d[59]), "+f"(d[60]), "+f"(d[61]), "+f"(d[62]), "+f"(d[63])
      : "l"(da), "l"(db), "r"(sc));
}

__device__ __forceinline__ void wgmma_ss_n40(float (&d)[20], uint64_t da, uint64_t db, int sc) {
  asm volatile("{\n.reg .pred p;\nsetp.ne.b32 p, %22, 0;\n"
      "wgmma.mma_async.sync.aligned.m64n40k16.f32.bf16.bf16 "
      "{%0,%1,%2,%3,%4,%5,%6,%7,%8,%9,%10,%11,%12,%13,%14,%15,%16,%17,%18,%19}, "
      "%20, %21, p, 1, 1, 1, 1;\n}\n"
      : "+f"(d[0]), "+f"(d[1]), "+f"(d[2]), "+f"(d[3]), "+f"(d[4]), "+f"(d[5]), "+f"(d[6]), "+f"(d[7]),
        "+f"(d[8]), "+f"(d[9]), "+f"(d[10]), "+f"(d[11]), "+f"(d[12]), "+f"(d[13]), "+f"(d[14]), "+f"(d[15]),
        "+f"(d[16]), "+f"(d[17]), "+f"(d[18]), "+f"(d[19])
      : "l"(da), "l"(db), "r"(sc));
}

__device__ __forceinline__ void wgmma_rs_n8(float (&d)[4], const uint4& a, uint64_t db, int sc) {
  asm volatile("{\n.reg .pred p;\nsetp.ne.b32 p, %9, 0;\n"
      "wgmma.mma_async.sync.aligned.m64n8k16.f32.bf16.bf16 "
      "{%0,%1,%2,%3}, "
      "{%4,%5,%6,%7}, %8, p, 1, 1, 1;\n}\n"
      : "+f"(d[0]), "+f"(d[1]), "+f"(d[2]), "+f"(d[3])
      : "r"(a.x), "r"(a.y), "r"(a.z), "r"(a.w), "l"(db), "r"(sc));
}

__device__ __forceinline__ void wgmma_rs_n16(float (&d)[8], const uint4& a, uint64_t db, int sc) {
  asm volatile("{\n.reg .pred p;\nsetp.ne.b32 p, %13, 0;\n"
      "wgmma.mma_async.sync.aligned.m64n16k16.f32.bf16.bf16 "
      "{%0,%1,%2,%3,%4,%5,%6,%7}, "
      "{%8,%9,%10,%11}, %12, p, 1, 1, 1;\n}\n"
      : "+f"(d[0]), "+f"(d[1]), "+f"(d[2]), "+f"(d[3]), "+f"(d[4]), "+f"(d[5]), "+f"(d[6]), "+f"(d[7])
      : "r"(a.x), "r"(a.y), "r"(a.z), "r"(a.w), "l"(db), "r"(sc));
}

__device__ __forceinline__ void wgmma_rs_n24(float (&d)[12], const uint4& a, uint64_t db, int sc) {
  asm volatile("{\n.reg .pred p;\nsetp.ne.b32 p, %17, 0;\n"
      "wgmma.mma_async.sync.aligned.m64n24k16.f32.bf16.bf16 "
      "{%0,%1,%2,%3,%4,%5,%6,%7,%8,%9,%10,%11}, "
      "{%12,%13,%14,%15}, %16, p, 1, 1, 1;\n}\n"
      : "+f"(d[0]), "+f"(d[1]), "+f"(d[2]), "+f"(d[3]), "+f"(d[4]), "+f"(d[5]), "+f"(d[6]), "+f"(d[7]),
        "+f"(d[8]), "+f"(d[9]), "+f"(d[10]), "+f"(d[11])
      : "r"(a.x), "r"(a.y), "r"(a.z), "r"(a.w), "l"(db), "r"(sc));
}

struct Params {
  const __nv_bfloat16 *logA, *Aim, *Cre, *Cim, *logdt, *Dskip, *x, *wphi, *wo;
  __nv_bfloat16* out;
  uint4* xs;
  long long* ts;
};

__device__ __forceinline__ uint4 tr_row(const uint4 (&v)[8], int i) {
  uint32_t o[4];
#pragma unroll
  for (int m = 0; m < 4; m++) {
    const uint4 &ra = v[2 * m], &rb = v[2 * m + 1];
    const int k = i >> 1;
    const uint32_t xa = k == 0 ? ra.x : k == 1 ? ra.y : k == 2 ? ra.z : ra.w;
    const uint32_t xb = k == 0 ? rb.x : k == 1 ? rb.y : k == 2 ? rb.z : rb.w;
    o[m] = __byte_perm(xa, xb, (i & 1) ? 0x7632 : 0x5410);
  }
  return make_uint4(o[0], o[1], o[2], o[3]);
}

struct cpx { float r, i; };
__device__ __forceinline__ cpx csq(cpx a) { return {a.r * a.r - a.i * a.i, 2.f * (a.r * a.i)}; }
__device__ __forceinline__ cpx polar(float e, float t) {
  const float m = ex2(e);
  return {m * __cosf(t), m * __sinf(t)};
}

struct KgenRaw { unsigned short la, ai, cr, ci, ldt; };
__device__ __forceinline__ KgenRaw kgen_load(const Params& P, int d, int unit, int lane) {
  const int o = d * 128 + unit * 32 + lane;
  return {__ldg((const unsigned short*)P.logA + o), __ldg((const unsigned short*)P.Aim + o), __ldg((const unsigned short*)P.Cre + o),
          __ldg((const unsigned short*)P.Cim + o), __ldg((const unsigned short*)P.logdt + d)};
}
struct hmul { __half2 a, b; };
__device__ __forceinline__ hmul mk_mul(cpx w) {
  uint32_t b;
  asm("{\n.reg .f32 n;\nneg.ftz.f32 n, %1;\ncvt.rn.f16x2.f32 %0, %2, n;\n}\n" : "=r"(b) : "f"(w.i), "f"(w.r));
  return {__floats2half2_rn(w.r, w.i), *(const __half2*)&b};
}
__device__ __forceinline__ __half2 hcm(__half2 z, const hmul& w) { return __hfma2(__high2half2(z), w.b, __hmul2(__low2half2(z), w.a)); }
__device__ __forceinline__ uint32_t hu(__half2 v) { return *(const uint32_t*)&v; }

struct KgenAddr { uint32_t sa, lb, lm[4]; };
__device__ __forceinline__ KgenAddr kgen_addr(int lane, uint32_t buf) {
  KgenAddr a;
  a.sa = buf + (lane & 7) * 128 + ((((lane >> 3) ^ lane) & 7) << 4);
  const int q = lane >> 3;
  a.lb = buf + q * 128 + (((lane ^ q) & 7) << 4);
  a.lm[0] = buf + q * 128 + (q << 4);
  a.lm[1] = buf + q * 128 + ((1 ^ q) << 4);
  a.lm[2] = buf + q * 128 + (((2 + (lane & 1)) ^ q) << 4);
  a.lm[3] = buf + q * 128 + (((4 + (lane & 3)) ^ q) << 4);
  asm volatile("" : "+r"(a.sa), "+r"(a.lb), "+r"(a.lm[0]), "+r"(a.lm[1]), "+r"(a.lm[2]), "+r"(a.lm[3]));
  return a;
}
__device__ __forceinline__ void kgen_unit(const KgenRaw& r, const KgenAddr& ad, uint32_t zero, float (&k)[5][4], float& k2048, float& sc) {
  const float dt = bf_round(expf(bf_lo(r.ldt)));
  const float a2 = bf_round(ex2(bf_lo(r.la) * 1.4426950408889634f)) * (dt * -1.4426950408889634f);
  const float f = bf_lo(r.ai) * dt;
  const float r127 = f * 20.21267777267071f;
  const uint32_t ex = min(max(__reduce_max_sync(0xffffffffu, max(r.cr & 0x7fffu, r.ci & 0x7fffu)) >> 7, 1u), 253u);
  const float cs = uf((254u - ex) << 23);
  sc = 2.f * dt * uf(ex << 23);
  const cpx C = {bf_lo(r.cr) * cs, -bf_lo(r.ci) * cs};
  auto put = [&](const __half2 (&v)[8]) {
    stsm4(ad.sa, hu(v[0]), hu(v[1]), hu(v[2]), hu(v[3]));
    stsm4(ad.sa ^ 64, hu(v[4]), hu(v[5]), hu(v[6]), hu(v[7]));
    __syncwarp();
  };
  auto get = [&](uint32_t (&o)[2][4], uint32_t a) { ldsm4(o[0], a); ldsm4(o[1], (a ^ 64) + 512); };
  auto rot = [](uint32_t z) { return __byte_perm(z, z, 0x1032) ^ 0x8000u; };
  auto fmul = [](uint32_t z, uint32_t zi, uint32_t w) {
    const __half2 hw = *(const __half2*)&w;
    return hu(__hfma2(*(const __half2*)&zi, __high2half2(hw), __hmul2(*(const __half2*)&z, __low2half2(hw))));
  };
  uint32_t A[4][4];
  auto tile = [&](int j, const uint32_t (&B)[2][4]) {
    k[j][0] = k[j][1] = k[j][2] = k[j][3] = 0.f;
#pragma unroll
    for (int s = 0; s < 4; s++) mma_h(k[j], A[s], B[s >> 1][2 * (s & 1)], B[s >> 1][2 * (s & 1) + 1]);
  };
  auto after = [&](cpx v, uint32_t dep) { return cpx{uf(fu(v.r) ^ (dep & zero)), v.i}; };
  const cpx w1 = polar(a2, f), w127 = polar(a2 * 127.f, (r127 - rintf(r127)) * 6.283185307179586f);
  const cpx w2 = csq(w1), w4 = csq(w2);
  uint32_t T0[2][4], A0[2][4], T4[2][4], M[4][2][4];
  {
    __half2 t[8];
    const hmul m2 = mk_mul(w2), m4 = mk_mul(w4);
    t[0] = __floats2half2_rn(1.f, 0.f); t[1] = __floats2half2_rn(w1.r, w1.i); t[2] = m2.a; t[4] = m4.a;
    t[3] = hcm(t[1], m2); t[5] = hcm(t[1], m4); t[6] = hcm(t[2], m4); t[7] = hcm(t[3], m4);
    put(t); get(T0, ad.lb);
  }
  cpx w8 = csq(w4);
  w8.i = -w8.i;
  const cpx w16 = csq(w8), w32 = csq(w16), w64 = csq(w32);
  {
    const hmul m8 = mk_mul(w8), m16 = mk_mul(w16), m32 = mk_mul(w32);
    __half2 a[8];
    a[0] = __floats2half2_rn(C.r, C.i); a[1] = hcm(a[0], m8);
    a[2] = hcm(a[0], m16); a[3] = hcm(a[1], m16);
#pragma unroll
    for (int i = 0; i < 4; i++) a[4 + i] = hcm(a[i], m32);
    put(a); get(A0, ad.lb);
  }
  const cpx w127b = after(w127, T0[0][0]);
  const cpx w128 = {w127b.r * w1.r - w127b.i * w1.i, w127b.r * w1.i + w127b.i * w1.r};
  const cpx w256 = csq(w128), w512 = csq(w256);
  const hmul m128 = mk_mul(w128), m256 = mk_mul(w256), m512 = mk_mul(w512);
  {
    const hmul m254 = mk_mul(csq(w127b));
    const __half2 h127 = __floats2half2_rn(w127b.r, w127b.i);
    __half2 m[8];
    m[0] = __floats2half2_rn(w64.r, w64.i); m[1] = m128.a; m[2] = m256.a; m[3] = hcm(h127, m256);
    m[4] = m512.a; m[5] = hcm(h127, m512); m[6] = hcm(m[4], m254); m[7] = hcm(m[5], m254);
    put(m);
#pragma unroll
    for (int i = 0; i < 4; i++) get(M[i], ad.lm[i]);
  }
  const cpx w1024 = csq(after(w512, A0[0][0])), we = csq(w1024);
  {
    __half2 t[8];
    t[0] = __floats2half2_rn(w1024.r, w1024.i); t[1] = hcm(t[0], m128);
    t[2] = hcm(t[0], m256); t[3] = hcm(t[1], m256);
#pragma unroll
    for (int i = 0; i < 4; i++) t[4 + i] = hcm(t[i], m512);
    put(t); get(T4, ad.lb);
  }
  k2048 = (C.r * we.r + C.i * we.i) * sc;
#pragma unroll
  for (int i = 0; i < 8; i++) {
    const uint32_t z = A0[i >> 2][i & 3];
    A[i >> 1][2 * (i & 1)] = z + zero;
    A[i >> 1][2 * (i & 1) + 1] = fmul(z, rot(z), M[0][i >> 2][i & 3]);
  }
  tile(0, T0);
#pragma unroll
  for (int i = 0; i < 8; i++) {
    const uint32_t z = T0[i >> 2][i & 3], zi = rot(z);
#pragma unroll
    for (int j = 1; j < 4; j++) M[j][i >> 2][i & 3] = fmul(z, zi, M[j][i >> 2][i & 3]);
  }
  tile(4, T4); tile(1, M[1]); tile(2, M[2]); tile(3, M[3]);
}

__device__ __forceinline__ void build_tables(uint32_t tb, int lane, float (&k)[5][4], float k2048) {
  const int g = lane >> 2, c = lane & 3;
  const uint32_t kc = tb + T_KC + 16;
  {
    const uint32_t a0 = kc + 16 * g + 4 * c, a2 = kc + 2 * (256 + 4 * g + c);
    const uint32_t a3 = kc + 2 * (384 + 2 * g + 64 * (c & 1) + (c >> 1)), a4 = kc + 2 * (512 + g + 32 * c);
#pragma unroll
    for (int r = 0; r < 2; r++) {
      sts32(a0 + 128 * r, pack_bf(k[0][2 * r], k[0][2 * r + 1]));
      sts32(a0 + 128 * r + 256, pack_bf(k[1][2 * r], k[1][2 * r + 1]));
      const uint32_t w2 = pack_bf(k[2][2 * r], k[2][2 * r + 1]);
      const uint32_t w3 = pack_bf(k[3][2 * r], k[3][2 * r + 1]);
      const uint32_t w4 = pack_bf(k[4][2 * r], k[4][2 * r + 1]);
      sts16(a2 + 64 * r, w2); sts16(a2 + 64 * r + 128, w2 >> 16);
      sts16(a3 + 32 * r, w3); sts16(a3 + 32 * r + 64, w3 >> 16);
      sts16(a4 + 16 * r, w4); sts16(a4 + 16 * r + 32, w4 >> 16);
    }
  }
  if (lane == 0) { sts16(kc + 2 * 640, pack_bf(k2048, 0.f)); sts32(kc - 4, 0); }
  __syncwarp();
  const uint32_t td = tb + T_D + 32;
#pragma unroll
  for (int hf = 0; hf < 2; hf++) {
    const uint2 v = lds64(kc + 256 * hf + 8 * lane);
    const uint32_t pv = lds32(kc + 256 * hf + 8 * lane - 4);
    sts128(td + 512 * hf + 16 * lane, __byte_perm(v.x, pv, 0x7610), __byte_perm(v.x, v.x, 0x1032), __byte_perm(v.y, v.x, 0x7610),
           __byte_perm(v.y, v.y, 0x1032));
  }
#pragma unroll
  for (int hf = 0; hf < 2; hf++) {
    const uint32_t v = lds32(kc + 512 + 128 * hf + 4 * lane), nx = lds32(kc + 516 + 128 * hf + 4 * lane);
    uint32_t w0 = __byte_perm(v, v, 0x1010);
    const uint32_t w1 = w0;
    if (hf == 0) { const uint32_t pv = lds32(kc + 508); if (lane == 0) w0 = __byte_perm(v, pv, 0x7610); }
    sts128(td + 1024 + 512 * hf + 16 * lane, w0, w1, __byte_perm(v, v, 0x1032), __byte_perm(nx, v, 0x7610));
  }
  {
    const uint32_t kk = lds16(kc + 2 * 384);
    const uint32_t w = lane < 3 ? (kk | (kk << 16)) : (lane == 3 ? (kk << 16) : 0u);
    if (lane < 24) sts32(td + 4 * (lane < 16 ? 512 + lane : lane - 24), w);
    const uint32_t lo_ = lds16(kc + 2 * 511), le_ = lds16(kc + 2 * 512);
    const uint32_t ja = tb + T_5 + (lane < 16 ? 4 * lane : 256 + 4 * lane);
    sts32(ja, lane == 16 ? (le_ << 16) : 0u);
    sts32(ja + 384, lane == 16 ? (lo_ << 16) : 0u);
    sts32(tb + (lane < 16 ? T_7 : T_9 - 64) + 4 * lane, 0u);
  }
#pragma unroll
  for (int s = 0; s < 2; s++) {
    const uint32_t b = kc + 2 * (s ? 512 : 384) + 8 * lane;
    const uint2 v = lds64(b);
    uint32_t em = lds16(b - 2), e0 = v.x;
    const uint32_t e4 = lds16(b + 8);
    if (lane == 0) { em = 0; e0 = 0; }
    sts64(tb + (s ? T_7 : T_3) + 64 + 8 * lane, __byte_perm(v.x, em, 0x5432), __byte_perm(v.y, v.x, 0x7632));
    sts64(tb + (s ? T_9 : T_5) + 64 + 8 * lane, __byte_perm(v.y, e0, 0x5410), __byte_perm(e4, v.y, 0x5410));
  }
  __syncwarp();
}

__device__ __forceinline__ uint32_t box2w(int lo, int n, int o) {
  return ((unsigned)(o - lo) < (unsigned)n ? 0x3F80u : 0u) | ((unsigned)(o + 1 - lo) < (unsigned)n ? 0x3F800000u : 0u);
}

__device__ __forceinline__ void conv_channel(uint32_t ub, uint32_t tb, int lane, uint4* ydst) {
  const int g = lane >> 2, c = lane & 3, x = g - 2 * c;
  const int mi = lane >> 3;
  const uint32_t qa = ub + U_PAD + 16 * (lane & 7) + ((mi == 0 || mi == 3) ? U_ODD : 0) - (mi == 0 ? 16 : 0);
  const uint32_t hb = ub + U_PAD + (mi & 1) * U_ODD + 16 * ((lane >> 4) + (lane & 7)) - 16;
  const uint32_t kv = lds16(tb + T_KC + 16 + 2 * 512);
  const int oh = c < 2 ? 8 + 2 * c : 2 * c - 8, og = c < 3 ? 2 * c : -10;
  uint32_t bx[4] = {box2w(g - 4, 9, 2 * c), box2w(g - 3, 7, 2 * c), box2w(g - 4, 9, oh), box2w(g - 3, 7, oh)};
  uint32_t by[4] = {box2w(g - 10, 5, 2 * c - 8), box2w(g - 5, 3, 2 * c - 8), box2w(g - 10, 5, og), box2w(g - 5, 3, og)};
  uint32_t lb0 = ((unsigned)(x + 5) < 2u ? kv : 0u) | ((unsigned)(x + 4) < 2u ? kv << 16 : 0u);
  uint32_t lb1 = ((unsigned)(x - 3) < 2u ? kv : 0u) | ((unsigned)(x - 4) < 2u ? kv << 16 : 0u);
  const int q0 = g - 1, q1 = c < 3 ? g : g - 2;
  uint32_t y0a = ub + U_PAD + (q0 & 1) * U_ODD + 16 * (q0 >> 1) + 4 * c;
  uint32_t y1a = ub + U_PAD + (q1 & 1) * U_ODD + 16 * (q1 >> 1) + 4 * c;
#pragma unroll
  for (int i = 0; i < 4; i++) asm volatile("" : "+r"(bx[i]), "+r"(by[i]));
  asm volatile("" : "+r"(lb0), "+r"(lb1), "+r"(y0a), "+r"(y1a));
  mbar_wait(BAR(MB_UFULL));
  mbar_spin(BAR(MB_EMPTY + 15));
  nb_sync(NB_GATE, 256);
  SPLIT();
  TS(36);
  float acc[16][4];
  {
    uint32_t z09[8], z07[8], zm9[8], zm7[8];
#pragma unroll
    for (int i = 0; i < 8; i++) {
      uint32_t h[4];
      ldsm4(h, hb + 128 * i);
      float y0, y1, y2, y3, w0, w1, w2, w3;
      mma0(y0, y1, y2, y3, bx[0], bx[1], bx[2], bx[3], h[2], c < 2 ? h[3] : h[1]);
      mma0(w0, w1, w2, w3, bx[0], bx[1], bx[2], bx[3], h[1], c < 2 ? h[2] : h[0]);
      z09[i] = pack_bf(y0, y1); z07[i] = pack_bf(y2, y3);
      zm9[i] = pack_bf(w0, w1); zm7[i] = pack_bf(w2, w3);
    }
  uint32_t f3[3][4][4];
  {
    const uint32_t fa = tb + T_7 + 4 * (16 + x);
#pragma unroll
    for (int tt = 0; tt < 3; tt++)
#pragma unroll
      for (int D = 0; D < 4; D++) {
        const uint32_t a = fa + (tt == 0 ? 316 : (tt == 1 ? 320 : 0)) + 64 * D;
        f3[tt][D][0] = lds32(a); f3[tt][D][1] = lds32(a + 32); f3[tt][D][2] = lds32(a - 32); f3[tt][D][3] = lds32(a);
      }
  }
    float a[4][2][4];
#pragma unroll
    for (int kap = 0; kap < 4; kap++)
#pragma unroll
      for (int sg = 0; sg < 2; sg++)
#pragma unroll
        for (int bk = 3; bk >= kap; bk--) {
          const uint32_t(&q0_)[4] = f3[sg ? 2 : 0][bk - kap];
          const uint32_t(&q1_)[4] = f3[sg ? 2 : 1][bk - kap];
          float(&a0)[4] = a[bk][0];
          float(&a1)[4] = a[bk][1];
          if (sg == 0 && kap == 0) {
            mma0(a0[0], a0[1], a0[2], a0[3], q0_[0], q0_[1], q0_[2], q0_[3], z09[0], z09[1]);
            mma0(a1[0], a1[1], a1[2], a1[3], q1_[0], q1_[1], q1_[2], q1_[3], zm9[0], zm9[1]);
          } else {
            mma(a0[0], a0[1], a0[2], a0[3], q0_[0], q0_[1], q0_[2], q0_[3], sg ? zm7[2 * kap] : z09[2 * kap], sg ? zm7[2 * kap + 1] : z09[2 * kap + 1]);
            mma(a1[0], a1[1], a1[2], a1[3], q1_[0], q1_[1], q1_[2], q1_[3], sg ? z07[2 * kap] : zm9[2 * kap], sg ? z07[2 * kap + 1] : zm9[2 * kap + 1]);
          }
        }
    SPLIT();
#pragma unroll
    for (int i = 0; i < 8; i++) {
      uint32_t h[4];
      ldsm4(h, qa + 128 * i);
      const float ci[4] = {a[i >> 1][0][2 * (i & 1)], a[i >> 1][0][2 * (i & 1) + 1], a[i >> 1][1][2 * (i & 1)], a[i >> 1][1][2 * (i & 1) + 1]};
      mmac(acc[8 + i], h[0], h[1], h[2], h[3], lb0, lb1, ci);
    }
  }
  TS(44);
  {
    uint2 a5[10], a3[10];
    const uint32_t aa = tb + T_5 + 4 * (8 + 2 * g - 2 * c);
#pragma unroll
    for (int m = 0; m < 10; m++) { a5[m] = lds64(aa + 32 * m); a3[m] = lds64(aa + 384 + 32 * m); }
    uint32_t x5[12][2], x3[12][2];
    auto ygen = [&](int kap) {
#pragma unroll
      for (int hh = 0; hh < 2; hh++) {
        float y0, y1, y2, y3;
        mma0(y0, y1, y2, y3, by[0], by[1], by[2], by[3], lds32(y0a + 128 * kap + 64 * hh), lds32(y1a + 128 * kap + 64 * hh));
        x5[kap][hh] = pack_bf(y0, y1);
        x3[kap][hh] = pack_bf(y2, y3);
      }
    };
    ygen(11); ygen(10); ygen(9); ygen(8);
#pragma unroll
    for (int kap = 11; kap >= 0; kap--) {
      if (kap >= 4) ygen(kap - 4);
#pragma unroll
      for (int sg = 0; sg < 2; sg++)
#pragma unroll
        for (int i = 4; i >= 0; i--) {
          const int be = kap + 4 + i;
          if (be <= 15) {
            const uint2 &hi = sg ? a3[2 * i + 1] : a5[2 * i + 1], &lo = sg ? a3[2 * i] : a5[2 * i];
            const uint32_t b0 = sg ? x3[kap][0] : x5[kap][0], b1 = sg ? x3[kap][1] : x5[kap][1];
            if (be < 8 && i == 0 && sg == 0) mma0(acc[be][0], acc[be][1], acc[be][2], acc[be][3], hi.x, hi.y, lo.x, lo.y, b0, b1);
            else mma(acc[be][0], acc[be][1], acc[be][2], acc[be][3], hi.x, hi.y, lo.x, lo.y, b0, b1);
          }
        }
    }
  }
  TS(45);
  {
    const uint32_t st = tb + T_ST + lane * 8;
#pragma unroll
    for (int be = 4; be < 12; be++) sts64(st + 256 * be, pack_bf(acc[be][0], acc[be][1]), pack_bf(acc[be][2], acc[be][3]));
    SPLIT();
    uint32_t F[66], qd[8][4];
    const uint32_t fa = tb + T_D + 32 + 4 * x;
#pragma unroll
    for (int i = 0; i < 32; i++) {
      const int s = 120 - (i >> 2) - 8 * (i & 3);
      uint32_t(&q)[4] = qd[i & 7];
      ldsm4(q, qa + 16 * s);
      const int m = 16 * (i & 3) + 2 * (i >> 2);
      F[m] = lds32(fa + 32 * m); F[m + 1] = lds32(fa + 32 * m + 32);
#pragma unroll
      for (int be = 15; be >= 12; be--) {
        const int de = 8 * be - s;
        float(&a)[4] = (be >= 14 && !(i & 1)) ? acc[be - 4] : acc[be];
        if (de >= 0 && be >= 14 && i == 2 * (15 - be)) mma0(a[0], a[1], a[2], a[3], q[0], q[1], q[2], q[3], F[2 * de + 1], F[2 * de]);
        else if (de >= 0) mma(a[0], a[1], a[2], a[3], q[0], q[1], q[2], q[3], F[2 * de + 1], F[2 * de]);
      }
    }
#pragma unroll
    for (int i = 0; i < 8; i++) acc[14 + (i >> 2)][i & 3] += acc[10 + (i >> 2)][i & 3];
    F[64] = lds32(fa + 32 * 64); F[65] = lds32(fa + 32 * 65);
#pragma unroll
    for (int i = 0; i < 6; i++) ldsm4(qd[i], qa + 128 * 11 - 16 * i);
    uint2 sv = lds64(st + 256 * 11);
    float ci[4] = {bf_lo(sv.x), bf_hi(sv.x), bf_lo(sv.y), bf_hi(sv.y)};
    float T[5][4];
#pragma unroll
    for (int i = 0; i < 16; i++) T[i >> 2][i & 3] = acc[12 + (i >> 2)][i & 3];
    nb_sync(NB_YZ, 160);
    TS(46);
    uint32_t held[2];
#pragma unroll
    for (int be = 11; be >= 0; be--) {
      if (be & 1) SPLITN(be);
      const uint32_t qp = qa + 128 * be;
#pragma unroll
      for (int k = 4; k >= 1; k--) mmac(T[k], qd[0][0], qd[0][1], qd[0][2], qd[0][3], F[16 * k + 1], F[16 * k], T[k - 1]);
      if (be >= 4) mmac(T[0], qd[0][0], qd[0][1], qd[0][2], qd[0][3], F[1], F[0], ci);
      else mma0(T[0][0], T[0][1], T[0][2], T[0][3], qd[0][0], qd[0][1], qd[0][2], qd[0][3], F[1], F[0]);
      ldsm4(qd[6], qp - 16 * 6);
      ldsm4(qd[7], qp - 16 * 7);
      if (be > 4) sv = lds64(st + 256 * (be - 1));
#pragma unroll
      for (int i = 1; i < 8; i++) {
#pragma unroll
        for (int k = 3; k >= 0; k--)
          mma(T[k][0], T[k][1], T[k][2], T[k][3], qd[i][0], qd[i][1], qd[i][2], qd[i][3], F[16 * k + 2 * i + 1], F[16 * k + 2 * i]);
        if (i < 7 && be > 0) ldsm4(qd[i - 1], qp - 128 - 16 * (i - 1));
        if (i == 2) {
          const uint32_t w0 = pack_bf(T[4][0], T[4][1]), w1 = pack_bf(T[4][2], T[4][3]);
          if (be & 1) { held[0] = w0; held[1] = w1; }
          else st_x(ydst + (be + 4) * 16, nz(w0), w1, held[0], held[1]);
          if ((be & 3) == 3 && be < 11) nb_arrive(NB_Y + 2 + (be >> 2), 160);
        }
        if (i == 4 && be > 4) { ci[0] = bf_lo(sv.x); ci[1] = bf_hi(sv.x); ci[2] = bf_lo(sv.y); ci[3] = bf_hi(sv.y); }
      }
    }
    nb_arrive(NB_Y + 1, 160);
#pragma unroll
    for (int B = 1; B >= 0; B--)
      st_x(ydst + B * 32, nz(pack_bf(T[2 * B][0], T[2 * B][1])), pack_bf(T[2 * B][2], T[2 * B][3]),
           pack_bf(T[2 * B + 1][0], T[2 * B + 1][1]), pack_bf(T[2 * B + 1][2], T[2 * B + 1][3]));
  }
}

__device__ __forceinline__ void dual_exp(const uint32_t* w, uint32_t* e) {
  const float L = 1.44268798828125f;
  uint32_t mx = bmax2(bmax2(w[0], w[1]), bmax2(w[2], w[3]));
  uint32_t mn = bmin2(bmin2(w[0], w[1]), bmin2(w[2], w[3]));
  mx = bmax2(mx, __shfl_xor_sync(0xffffffffu, mx, 1));
  mn = bmin2(mn, __shfl_xor_sync(0xffffffffu, mn, 1));
  mx = bmax2(mx, __shfl_xor_sync(0xffffffffu, mx, 2));
  mn = bmin2(mn, __shfl_xor_sync(0xffffffffu, mn, 2));
  const float mx0 = bf_lo(mx) * -L, mx1 = bf_hi(mx) * -L, mn0 = bf_lo(mn) * L, mn1 = bf_hi(mn) * L;
#pragma unroll
  for (int i = 0; i < 2; i++) {
    const float a0 = bf_lo(w[2 * i]), a1 = bf_hi(w[2 * i]), b0 = bf_lo(w[2 * i + 1]), b1 = bf_hi(w[2 * i + 1]);
    e[2 * i] = pack_bf(ex2(fmaf(a0, L, mx0)), ex2(fmaf(b0, L, mx0)));
    e[2 * i + 1] = pack_bf(ex2(fmaf(a1, L, mx1)), ex2(fmaf(b1, L, mx1)));
    e[4 + 2 * i] = pack_bf(ex2(fmaf(a0, -L, mn0)), ex2(fmaf(b0, -L, mn0)));
    e[5 + 2 * i] = pack_bf(ex2(fmaf(a1, -L, mn1)), ex2(fmaf(b1, -L, mn1)));
  }
}
__device__ __forceinline__ void normalise(uint32_t* e, const float (&s)[4]) {
  const uint32_t r = pack_bf(rcp(s[0]), rcp(s[2]));
  const __nv_bfloat162 rr = *(const __nv_bfloat162*)&r;
#pragma unroll
  for (int i = 0; i < 4; i++) {
    const __nv_bfloat162 v = __hmul2(*(const __nv_bfloat162*)&e[i], (i & 1) ? __high2bfloat162(rr) : __low2bfloat162(rr));
    e[i] = *(const uint32_t*)&v;
  }
}
__host__ __device__ constexpr uint64_t qdesc(uint32_t addr) { return mkdesc(addr, 128, 256, 0); }

__global__ void __launch_bounds__(NTHREADS, 1)
fused_kernel(const Params P, const __grid_constant__ CUtensorMap mx, const __grid_constant__ CUtensorMap mw,
             const __grid_constant__ CUtensorMap mo, const __grid_constant__ CUtensorMap mu,
             const __grid_constant__ CUtensorMap mout, const __grid_constant__ CUtensorMap mw4) {
  constexpr uint32_t sb = SB;
  const int tid = threadIdx.x, lane = tid & 31;
  const int warp = __shfl_sync(0xffffffffu, tid >> 5, 0);
  const int b = blockIdx.x, oct = b >> 3, i8 = b & 7;
  const int rt = (((oct & 4) ? ~oct : oct) & 3) * 2 + (i8 >> 2);
  const int hp = (oct >> 2) * 4 + (i8 & 3);

  const int wg = warp >> 2, w = warp & 3;
  const int d = b * 4 + ((tid >> 5) & 3);
  const KgenRaw raw = kgen_load(P, d, tid >> 7, lane);
  const unsigned short dsk = __ldg((const unsigned short*)P.Dskip + d);
  if (warp == 15) {
    asm volatile("prefetch.tensormap [%0];" ::"l"(&mu) : "memory");
    asm volatile("prefetch.tensormap [%0];" ::"l"(&mw) : "memory");
    asm volatile("prefetch.tensormap [%0];" ::"l"(&mx) : "memory");
    asm volatile("prefetch.tensormap [%0];" ::"l"(&mw4) : "memory");
  }
  if (warp == 12) {
    if (lane == 0) {
#pragma unroll
      for (int i = 0; i < 9; i++) mbar_init(BAR(i), 1);
      asm volatile("fence.mbarrier_init.release.cluster;" ::: "memory");
    }
    __syncwarp();
    if (lane < 9) mbar_expect(BAR(0) + 8 * lane, (lane == 5 || lane == 7) ? 40960 : ((lane == 0 || lane > 5) ? 16384 : 28672));
    __syncwarp();
    e_tma3d(sb + OFF_W, &mw, BAR(MB_FULL), hp * 32, 0, 0);
    e_tma2d(sb + OFF_X + 3 * 16384, &mx, BAR(MB_FULL), 0, rt * 256);
    nb_arrive(NB_PROD, 512);
  } else if (warp == 14) {
    e_prefetch(P.x + (size_t)(rt * 256 + hp * 8) * 512, 8192);
  } else if (warp == 13) {
    if (lane == 0) {
#pragma unroll
      for (int i = 9; i < 40; i++) mbar_init(BAR(i), i < MB_EMPTY ? 1 : 4);
      asm volatile("fence.mbarrier_init.release.cluster;" ::: "memory");
    }
    __syncwarp();
    if (lane < 14 && lane != 9) mbar_expect(BAR(MB_FULL + 8) + 8 * lane, lane == 8 ? 131072 : (lane == 10 ? 8192 : (lane == 13 ? 24576 : 16384)));
    nb_arrive(NB_PROD, 512);
  }
  const uint32_t tb = sb + OFF_T + w * T_CH;
  const uint32_t kp = wg == 2 ? sb + OFF_STG0 + 16384 + w * 1024 : ((tb + 127) & ~127u) + (wg == 3 ? 2 : wg) * 1536;
  const KgenAddr kad = kgen_addr(lane, kp);
  if ((warp >> 1) != 6) nb_sync(NB_PROD, 512);
  else nb_sync(NB_GATE + 1, 64);
  if (warp == 12) {
#pragma unroll 1
    for (int kb = 1; kb < 4; kb++) {
      if (kb == U_AT) e_tma4d(sb + OFF_STG0, &mu, BAR(MB_URAW), i8 * 64, oct * 2);
      e_tma3d(sb + OFF_W + kb * 12288, &mw, BAR(MB_FULL) + 8 * kb, hp * 32, kb * 64, 0);
      e_tma2d(sb + OFF_X + (kb < 2 ? kb + 3 : kb - 2) * 16384, &mx, BAR(MB_FULL) + 8 * kb, kb * 64, rt * 256);
    }
    e_tma4d(sb + OFF_W + 4 * 12288, &mw4, BAR(MB_FULL + 4), hp * 32, 4);
    e_tma2d(sb + OFF_X + 2 * 16384, &mx, BAR(MB_FULL + 4), 256, rt * 256);
    e_tma4d(sb + OFF_W + 6 * 12288, &mw4, BAR(MB_FULL + 6), hp * 32, 6);
    if (smem_u32(smem_raw) != SB) __trap();
    if (lane == 0) TS1(54);
  }
  float k[5][4], k2048, ksc;
  kgen_unit(raw, kad, blockIdx.y, k, k2048, ksc);
  TS(40 + wg);
  if ((fu(k[0][0]) & fu(k[1][0]) & fu(k[2][0]) & fu(k[3][0]) & fu(k[4][0])) == 0xffffffffu) sts32(kp, 0);
  if (wg) nb_arrive(0, 512);
  if (wg != 2) {
    uint32_t h[10];
#pragma unroll
    for (int j = 0; j < 10; j++) h[j] = hu(__floats2half2_rn(k[j >> 1][2 * (j & 1)], k[j >> 1][2 * (j & 1) + 1]));
    sts128(kp + lane * 16, h[0], h[1], h[2], h[3]);
    sts128(kp + 512 + lane * 16, h[4], h[5], h[6], h[7]);
    sts128(kp + 1024 + lane * 16, h[8], h[9], fu(k2048), fu(ksc));
    nb_arrive(NB_PREP, 512);
    if (wg == 0) nb_sync(0, 512);
  } else {
    nb_sync(NB_PREP, 512);
  }
  if (warp >= 12) {
    asm volatile("setmaxnreg.dec.sync.aligned.u32 32;");
    if (warp == 12) {
      if (X2_AT < 0) e_prefetch(P.x + (size_t)(rt * 256 + 128 + hp * 8) * 512, 8192);
      uint32_t slot = sb + OFF_X + 3 * 16384;
#pragma unroll 1
      for (int n = 0; n < 11; n++) {
        mbar_spin(BAR(MB_EMPTY) + 8 * n);
        const int m = n + 5;
        e_tma2d(slot, &mx, BAR(MB_FULL) + 8 * m, (m & 7) * 64, rt * 256 + (m >> 3) * 128);
        slot = slot == sb + OFF_X + 4 * 16384 ? sb + OFF_X : slot + 16384;
        if (n == X2_AT) e_prefetch(P.x + (size_t)(rt * 256 + 128 + hp * 8) * 512, 8192);
        if (n == 7) {
          e_prefetch(P.wo + (size_t)b * 2048, 4096);
          asm volatile("prefetch.tensormap [%0];" ::"l"(&mo) : "memory");
          asm volatile("prefetch.tensormap [%0];" ::"l"(&mout) : "memory");
        }
      }
#pragma unroll 1
      for (int i = 0; i < 8; i++) {
        mbar_wait(BAR(MB_EMPTY + 10) + 8 * ((0x54332222u >> (4 * i)) & 7));
        const int w0 = (0x54736210u >> (4 * i)) & 7;
        e_tma3d(sb + OFF_W + w0 * 16384, &mo, BAR(MB_WO), 0, w0 * 64, (hp & 3) * 2);
      }
    } else {
      if (warp == 15) {
        const uint4 v0 = __ldg((const uint4*)P.wphi + hp * 64 + lane), v1 = __ldg((const uint4*)P.wphi + hp * 64 + 32 + lane);
        sts128(sb + OFF_PHI + (lane & 1) * 256 + (lane >> 1) * 16, v0.x, v0.y, v0.z, v0.w);
        sts128(sb + OFF_PHI + 512 + (lane & 1) * 256 + (lane >> 1) * 16, v1.x, v1.y, v1.z, v1.w);
        const uint32_t one = (((lane >> 3) ^ (lane >> 4)) & 1) ? 0u : ((lane & 1) ? 0x3F800000u : 0x3F80u);
        const int q = (lane >> 1) & 3;
        sts128(sb + OFF_EYE + lane * 16, q == 0 ? one : 0u, q == 1 ? one : 0u, q == 2 ? one : 0u, q == 3 ? one : 0u);
        sts64(sb + OFF_ONE + lane * 8, 0x3F803F80u, 0x3F803F80u);
        asm volatile("fence.proxy.async.shared::cta;" ::: "memory");
        nb_arrive(NB_KREAD, 160);
      }
      uint32_t* cnt = (uint32_t*)(P.xs + X_CNT) + (warp == 13 ? i8 : (warp == 14 ? 8 + rt : 16 + oct)) * 32;
      const unsigned target = (ld_x32(cnt) & ~15u) + 16;
      if (warp != 14) {
        if (warp == 15) mbar_wait(BAR(MB_EMPTY + ZERO_STEP));
        uint4* pz = P.xs + (warp == 13 ? X_PART + (hp * 8 + rt) * 144 : X_Y + b * 1024) + lane;
#pragma unroll 1
        for (int i = (warp == 13 ? 144 : 1024) - lane; i > 0; i -= 32, pz += 32) st_x(pz, 0, 0, 0, 0);
      }
      if (warp == 15) __syncwarp();
      else nb_sync(warp == 13 ? NB_INIT : NB_ODONE, warp == 13 ? 160 : 288);
      if (lane == 0) asm volatile("red.release.gpu.global.add.u32 [%0], %1;" ::"l"(cnt), "r"(warp == 15 ? 2 : 1) : "memory");
      if (lane == 0) TS1(warp == 13 ? 50 : (warp == 14 ? 57 : 53));
      __syncwarp();
      if (warp == 14) nb_arrive(NB_GATE + 1, 160);
      asm volatile("fence.proxy.async.shared::cta;" ::: "memory");
      if (warp == 13) cnt += ((lane & 1 ? b >> 4 : i8 ^ (lane & 4)) - i8) * 32;
#pragma unroll 1
      for (int i = 0; i < SPIN_MAX; i++) {
        unsigned v;
        asm volatile("ld.acquire.gpu.global.u32 %0, [%1];" : "=r"(v) : "l"(cnt) : "memory");
        if (__all_sync(0xffffffffu, (int)(v - target) >= 0)) break;
      }
      if (lane == 0) TS1(warp == 13 ? 51 : (warp == 14 ? 58 : 55));
      if (warp == 15) { nb_arrive(NB_YZ, 160); return; }
      asm volatile("fence.proxy.async.global;" ::: "memory");
      if (warp == 13) {
        mbar_wait(BAR(MB_EMPTY + 11));
        e_expect(BAR(MB_UFULL), 4 * U_CH);
        e_bulk(sb + OFF_U, P.xs + X_UT + b * (U_CH / 4), 4 * U_CH, BAR(MB_UFULL));
      } else {
        const uint4* src = P.xs + X_O + (rt * 4 + (hp >> 2)) * 4096;
        e_bulk(sb + OFF_X + 32768 + 57344, src + 3584, 8192, BAR(MB_O));
        e_bulk(sb + OFF_X + 32768, src, 16384, BAR(MB_O + 1));
        e_bulk(sb + OFF_X + 49152, src + 1024, 16384, BAR(MB_O + 2));
        e_bulk(sb + OFF_STG0, src + 3200, 6144, BAR(MB_O + 3));
        nb_sync(NB_BDONE, 288);
        asm volatile("fence.proxy.async.shared::cta;" ::: "memory");
        e_bulk(sb + OFF_U, src + 2048, 18432, BAR(MB_O + 3));
      }
    }
    return;
  }

  const int t = tid & 127;
  const int g = lane >> 2, c = lane & 3;
  if (wg == 1) {
    mbar_wait(BAR(MB_URAW));
    TS(48);
    uint4* dst = P.xs + X_UT + (i8 * 64 + g) * (U_CH / 16) + (w & 1) * (U_ODD / 16) + U_PAD / 16 + oct * 8 + (w >> 1) * 4 + c;
    const int ln = ((lane >> 1) & 3) + 4 * (lane & 1);
    uint32_t r[8][4];
#pragma unroll
    for (int i = 0; i < 8; i++) ldsm4t(r[i], sb + OFF_STG0 + w * 4096 + ((lane >> 3) * 8 + ln) * 128 + ((i ^ ln) << 4));
#pragma unroll
    for (int i = 0; i < 8; i++) dst[i * (U_CH / 2)] = make_uint4(r[i][0], r[i][1], r[i][2], r[i][3]);
    nb_arrive(NB_INIT, 160);
    if (lane == 0) mbar_arrive(BAR(MB_AUX));
  }
  {
    if (wg == 2) {
      asm volatile("setmaxnreg.inc.sync.aligned.u32 160;");
#pragma unroll
      for (int j = 0; j < 5; j++) { k[j][0] *= ksc; k[j][1] *= ksc; k[j][2] *= ksc; k[j][3] *= ksc; }
#pragma unroll 1
      for (int q = 0; q < 3; q++) {
        const uint32_t src = ((tb + 127) & ~127u) + q * 1536 + lane * 16;
        const uint4 v0 = lds128(src), v1 = lds128(src + 512), v2 = lds128(src + 1024);
        const uint32_t h[10] = {v0.x, v0.y, v0.z, v0.w, v1.x, v1.y, v1.z, v1.w, v2.x, v2.y};
#pragma unroll
        for (int j = 0; j < 10; j++) {
          const float2 f = __half22float2(*(const __half2*)&h[j]);
          k[j >> 1][2 * (j & 1)] = fmaf(f.x, uf(v2.w), k[j >> 1][2 * (j & 1)]);
          k[j >> 1][2 * (j & 1) + 1] = fmaf(f.y, uf(v2.w), k[j >> 1][2 * (j & 1) + 1]);
        }
        k2048 += uf(v2.z);
      }
#pragma unroll
      for (int o2 = 16; o2; o2 >>= 1) k2048 += __shfl_xor_sync(0xffffffffu, k2048, o2);
      if (lane == 0) k[0][0] += bf_lo(dsk);
      __syncwarp();
      TS(34);
      build_tables(tb, lane, k, k2048);
      TS(35);
      uint4* const g_y = P.xs + X_Y;
      conv_channel(sb + OFF_U + w * U_CH, tb, lane, g_y + (size_t)d * 256 + lane);
      nb_arrive(NB_BDONE, 288);
      nb_arrive(NB_Y, 160);
      TS(37);
      if (w == 0) TSDUMP(32);
      return;
    }
    if (wg == 1) {
      mbar_wait(BAR(MB_EMPTY + 4));
      mbar_spin(BAR(MB_EMPTY + 6));
    }
    TS(wg * 16 + 1);
  }

  float acc[2][48];
  {
    uint32_t fb = BAR(MB_FULL) + 64 * wg;
    uint32_t da = (uint32_t)mkdesc(sb + OFF_X, 16, 0, 0) + (wg ? 1024 : 3072), db = (uint32_t)mkdesc(sb + OFF_W, 4096, 0, 0);
    constexpr uint64_t ha = mkdesc(0, 0, 1024, 1), hb = mkdesc(0, 0, 512, 2);
    mbar_spin(fb);
    TS(wg * 16 + 2);
#pragma unroll 1
    for (int kb = 0; kb < 8; kb++) {
      WG_FENCE();
#pragma unroll
      for (int k = 0; k < 4; k++) {
        wgmma_ss_n96(acc[0], ha | (da + 2 * k), hb | (db + 64 * k), k ? 1 : kb);
        wgmma_ss_n96(acc[1], ha | (da + 2 * k + 512), hb | (db + 64 * k), k ? 1 : kb);
      }
      WG_COMMIT();
      if (kb < 7) mbar_spin(fb + 8);
      WG_WAIT(1);
      if (kb > 0) e_arrive(fb + 8 * (MB_EMPTY - MB_FULL - 1));
      fb += 8; db += 768;
      da = da == (uint32_t)mkdesc(sb + OFF_X + 65536, 16, 0, 0) ? da - 4096 : da + 1024;
    }
    if (wg == 0) nb_sync(NB_KREAD, 160);
    asm volatile("setmaxnreg.inc.sync.aligned.u32 160;");
    WG_WAIT(0);
    e_arrive(fb + 8 * (MB_EMPTY - MB_FULL - 1));
    SPLIT();
  }
  TS(wg * 16 + 3);

  constexpr uint32_t stg0 = sb + OFF_STG0, stg1 = sb + OFF_X + 32768;
  uint4* const g_part = P.xs + X_PART;
  uint4* const g_o = P.xs + X_O;
  constexpr uint32_t kvs = stg0;
  auto pack8 = [](const float* a) { return make_uint4(pack_bf(a[0], a[1]), pack_bf(a[2], a[3]), pack_bf(a[4], a[5]), pack_bf(a[6], a[7])); };
  auto feat = [&](const uint4 (&af)[4], float (&p)[4][8]) {
    WG_FENCE();
#pragma unroll
    for (int u = 0; u < 4; u++) wgmma_rs_n16(p[u], af[u], qdesc(sb + OFF_PHI + (u & 1) * 512), 0);
    WG_COMMIT();
  };
  auto packp = [](const float (&p)[4][8], uint32_t (&pw)[16]) {
#pragma unroll
    for (int i = 0; i < 16; i++) pw[i] = pack_bf(p[i >> 2][(i & 1) + 2 * (i & 2)], p[i >> 2][(i & 1) + 2 * (i & 2) + 2]);
  };
  auto contract = [&](float (&kc)[20], uint32_t stg, int acc_in) {
    WG_FENCE();
#pragma unroll
    for (int s = 0; s < 8; s++) wgmma_ss_n40(kc, qdesc(stg + s * SLAB), qdesc(stg + s * SLAB + 2048), s ? 1 : acc_in);
    WG_COMMIT();
    WG_WAIT(0);
  };
  uint32_t eq[32];
  {
    uint4 af[4], aq[4], vp[4];
    float p[4][8];
#pragma unroll
    for (int u = 0; u < 4; u++) af[u] = pack8(acc[u >> 1] + 16 + 8 * (u & 1));
    feat(af, p);
#pragma unroll
    for (int u = 0; u < 4; u++) { aq[u] = pack8(acc[u >> 1] + 8 * (u & 1)); vp[u] = pack8(acc[u >> 1] + 32 + 8 * (u & 1)); }
    WG_WAIT(0);
    uint32_t pw[16], ek[32];
    packp(p, pw);
#pragma unroll
    for (int u = 0; u < 4; u++) dual_exp(pw + 4 * u, ek + 8 * u);
    TS(wg * 16 + 12);
    if (wg && (ek[0] & ek[8] & ek[16] & ek[31]) != 0xffffffffu) nb_arrive(NB_GATE, 256);
    mbar_spin(wg ? BAR(MB_EMPTY + 15) : BAR(MB_AUX));
    float rs[8][4];
    WG_FENCE();
#pragma unroll
    for (int i = 0; i < 8; i++) wgmma_rs_n8(rs[i], make_uint4(ek[4 * i], ek[4 * i + 1], ek[4 * i + 2], ek[4 * i + 3]), qdesc(sb + OFF_ONE), 0);
    WG_COMMIT();
    feat(aq, p);
    const uint32_t sl = (wg ? stg1 : stg0) + w * SLAB + lane * 16;
#pragma unroll
    for (int i = 0; i < 4; i++) stsm4(sl + (i >> 1) * 4 * SLAB + 2048 + (i & 1) * 512, vp[i].x, vp[i].y, vp[i].z, vp[i].w);
    sts128(sl + (lane >> 4) * (4 * SLAB - 256) + 3072, 0x3F803F80u, 0x3F803F80u, 0x3F803F80u, 0x3F803F80u);
    WG_WAIT(1);
#pragma unroll
    for (int i = 0; i < 8; i++) {
      normalise(ek + 4 * i, rs[i]);
      stsm4(sl + (i >> 2) * 4 * SLAB + (i & 3) * 512, ek[4 * i], ek[4 * i + 1], ek[4 * i + 2], ek[4 * i + 3]);
    }
    asm volatile("fence.proxy.async.shared::cta;" ::: "memory");
    TS(wg * 16 + 13);
    if (wg) {
      nb_arrive(NB_ST0, 256);
    } else {
      float kc[20];
      uint4* pp = g_part + (size_t)(hp * 8 + rt) * 144 + t;
      uint32_t* pz = (uint32_t*)(pp - t + 128) + w * 16 + c * 8 + g;
      asm volatile("" : "+l"(pp), "+l"(pz));
      nb_sync(NB_WG0, 128);
      contract(kc, stg0, 0);
      mbar_wait(BAR(MB_UFULL));
      TS(15);
      nb_sync(NB_ST0, 256);
      contract(kc, stg1, 1);
      TS(6);
      float kv[8];
#pragma unroll
      for (int i = 0; i < 8; i++) kv[i] = w & 2 ? kc[8 + i] : kc[i];
      st_x(pp, nz(pack_bf(kv[0], kv[1])), pack_bf(kv[2], kv[3]), pack_bf(kv[4], kv[5]), pack_bf(kv[6], kv[7]));
      if (c < 2) st_x32(pz, nz(fu(c ? kc[18] : kc[16])));
      TS(5);
    }
    SPLIT();
    WG_WAIT(0);
    packp(p, pw);
#pragma unroll
    for (int u = 0; u < 4; u++) dual_exp(pw + 4 * u, eq + 8 * u);
    SPLIT();
  }
  TS(wg * 16 + 4);
  if (wg == 1) {
    mbar_wait(BAR(MB_UFULL));
    const uint4* ps = g_part + (size_t)hp * 8 * 144 + t;
    const uint32_t* zs = (const uint32_t*)(g_part + (size_t)(hp * 8 + (lane >> 4) * 4) * 144 + 128) + w * 16 + (lane & 15);
    uint4 v[8];
    uint32_t zv[4];
#pragma unroll 1
    for (int it = 0; it < SPIN_MAX; it++) {
#pragma unroll
      for (int i = 0; i < 8; i++) v[i] = ld_x(ps + i * 144);
#pragma unroll
      for (int i = 0; i < 4; i++) zv[i] = ld_x32(zs + i * 576);
      uint32_t m = min(min(zv[0], zv[1]), min(zv[2], zv[3]));
#pragma unroll
      for (int i = 0; i < 8; i++) m = min(m, v[i].x);
      if (__all_sync(0xffffffffu, m != 0)) break;
    }
    float s[8];
    WG_FENCE();
#pragma unroll
    for (int r = 0; r < 8; r++) wgmma_rs_n16(s, v[r], qdesc(sb + OFF_EYE), r);
    WG_COMMIT();
    float zsum = (uf(zv[0]) + uf(zv[1])) + (uf(zv[2]) + uf(zv[3]));
    zsum += __shfl_xor_sync(0xffffffffu, zsum, 16);
    const uint32_t z1 = pack_bf(zsum, 1.f);
    if (lane < 16) sts128(kvs + w * 768 + 512 + lane * 16, z1, z1, z1, z1);
    WG_WAIT(0);
    stsm4(kvs + w * 768 + lane * 16, pack_bf(s[0], s[1]), pack_bf(s[2], s[3]), pack_bf(s[4], s[5]), pack_bf(s[6], s[7]));
    asm volatile("fence.proxy.async.shared::cta;" ::: "memory");
    TS(22);
  }
  nb_sync(NB_KV, 256);
  {
    float n[8][12];
    WG_FENCE();
#pragma unroll
    for (int i = 0; i < 8; i++) wgmma_rs_n24(n[i], make_uint4(eq[4 * i], eq[4 * i + 1], eq[4 * i + 2], eq[4 * i + 3]), qdesc(kvs + (i & 3) * 768), 0);
    WG_COMMIT();
    uint32_t* od = (uint32_t*)(g_o + (size_t)((rt * 4 + wg * 2) * 32 + hp * 2) * 128) + w * 64 + lane;
    WG_WAIT(0);
#pragma unroll
    for (int u = 0; u < 4; u++) {
      float(&np)[12] = n[2 * u];
      const float(&nm)[12] = n[2 * u + 1];
      const float q0 = np[9] * rcp(nm[9]), q1 = np[11] * rcp(nm[11]);
      const float r0 = rcp(fmaf(nm[8], q0, fmaf(np[9], 1e-6f, np[8]))), r1 = rcp(fmaf(nm[10], q1, fmaf(np[11], 1e-6f, np[10])));
#pragma unroll
      for (int i = 0; i < 8; i++) np[i] = fmaf(nm[i], (i & 2) ? q1 : q0, np[i]);
      uint32_t* o = od + (u >> 1) * 16384 + (u & 1) * 512;
      o[0] = pack_bf(np[0] * r0, np[1] * r0);
      o[32] = pack_bf(np[2] * r1, np[3] * r1);
      o[256] = pack_bf(np[4] * r0, np[5] * r0);
      o[288] = pack_bf(np[6] * r1, np[7] * r1);
      if (u == 1) SPLIT();
    }
  }
  TS(wg * 16 + 7);
  nb_arrive(NB_ODONE, 288);
  if (wg) {
    const uint4* src = P.xs + X_Y + (oct * 32 + c * 8) * 256 + (2 * w + (g >> 2)) * 32 + i8 * 4 + (g & 3);
    __nv_bfloat16* dst = P.out + (size_t)((2 * w + (g >> 2)) * 256 + i8 * 16 + (g & 3) * 2) * 1024 + 512 + oct * 32 + c * 8;
    nb_sync(NB_GATE + 1, 160);
    nb_sync(NB_Y + w, 160);
    uint4 v[8];
#pragma unroll 1
    for (int it = 0; it < SPIN_MAX; it++) {
      uint32_t m = 0xffffffffu;
#pragma unroll
      for (int i = 0; i < 8; i++) v[i] = ld_x(src + i * 256);
#pragma unroll
      for (int i = 0; i < 8; i++) m = min(m, v[i].x);
      if (__all_sync(0xffffffffu, m != 0)) break;
    }
#pragma unroll
    for (int i = 0; i < 8; i++) *(uint4*)(dst + (size_t)((i >> 2) * 128 + ((i >> 1) & 1) * 8 + (i & 1)) * 1024) = tr_row(v, i);
    TS(31);
    GT(63);
    if (w == 0) TSDUMP(16);
    return;
  }
  mbar_wait(BAR(MB_WO));
  nb_sync(NB_BDONE, 288);
  TS(8);
  mbar_spin(BAR(MB_O));
  TS(9);
  constexpr uint64_t ha = mkdesc(0, 0, 128, 0), hb = mkdesc(0, 0, 1024, 1);
  constexpr uint32_t da0 = (uint32_t)mkdesc(stg1, 1024, 0, 0), db0 = (uint32_t)mkdesc(sb + OFF_W, 8192, 0, 0);
  const uint32_t ot = ((sb + OFF_T + 1023) & ~1023u) + w * 4096;
  auto store_half = [&](const float* oc, int hf) {
#pragma unroll
    for (int i = 0; i < 8; i += 2)
      stsm4(ot + hf * 2048 + (lane & 15) * 128 + (((i + (lane >> 4)) ^ lane) & 7) * 16, pack_bf(oc[4 * i], oc[4 * i + 1]),
            pack_bf(oc[4 * i + 2], oc[4 * i + 3]), pack_bf(oc[4 * i + 4], oc[4 * i + 5]), pack_bf(oc[4 * i + 6], oc[4 * i + 7]));
    asm volatile("fence.proxy.async.shared::cta;" ::: "memory");
    __syncwarp();
    e_store2d(&mout, ot + hf * 2048, (hp & 3) * 128 + hf * 64, (rt * 4 + (hp >> 2)) * 64 + w * 16);
  };
  float oc[64];
#pragma unroll 1
  for (int j = 0; j < 8; j++) {
    const int kb = (j + 7) & 7;
    if ((j & 1) && j < 6) mbar_spin(BAR(MB_O + 1) + 4 * (j - 1));
    WG_FENCE();
#pragma unroll
    for (int k = 0; k < 4; k++) wgmma_ss_n128(oc, ha | (da0 + 512 * kb + 128 * k), hb | (db0 + 1024 * kb + 128 * k), k ? 1 : j);
    WG_COMMIT();
  }
  WG_WAIT(0);
  TS(10);
  store_half(oc, 0);
  store_half(oc + 32, 1);
  asm volatile(ELECT "cp.async.bulk.commit_group;\n@p cp.async.bulk.wait_group.read 0;\n}\n" ::: "memory");
  TS(wg * 16 + 11);
  GT(61 + wg);
  if (w == 0) TSDUMP(0);
  if (w == 1) TSDUMP(48);
}

typedef CUresult (*EncodeFn)(CUtensorMap*, CUtensorMapDataType, cuuint32_t, void*, const cuuint64_t*, const cuuint64_t*,
                             const cuuint32_t*, const cuuint32_t*, CUtensorMapInterleave, CUtensorMapSwizzle,
                             CUtensorMapL2promotion, CUtensorMapFloatOOBfill);

}

extern "C" void kernel_launch(void* const* d_in, const int* in_sizes, int n_in, void* d_out, int out_size) {
  (void)in_sizes; (void)n_in; (void)out_size;
  void* fn = nullptr;
  cudaDriverEntryPointQueryResult qr;
  cudaGetDriverEntryPoint("cuTensorMapEncodeTiled", &fn, cudaEnableDefault, &qr);
  EncodeFn enc = (EncodeFn)fn;
  CUtensorMap mx, mw, mo, mu, mout, mw4;
  const cuuint32_t es[5] = {1, 1, 1, 1, 1};
  {
    cuuint64_t dims[2] = {512, 2048}, st[1] = {1024};
    cuuint32_t box[2] = {64, 128};
    enc(&mx, CU_TENSOR_MAP_DATA_TYPE_BFLOAT16, 2, d_in[0], dims, st, box, es, CU_TENSOR_MAP_INTERLEAVE_NONE,
        CU_TENSOR_MAP_SWIZZLE_128B, CU_TENSOR_MAP_L2_PROMOTION_L2_128B, CU_TENSOR_MAP_FLOAT_OOB_FILL_NONE);
  }
  {
    cuuint64_t dims[3] = {512, 512, 3}, st[2] = {3072, 1024};
    cuuint32_t box[3] = {32, 64, 3};
    enc(&mw, CU_TENSOR_MAP_DATA_TYPE_BFLOAT16, 3, d_in[1], dims, st, box, es, CU_TENSOR_MAP_INTERLEAVE_NONE,
        CU_TENSOR_MAP_SWIZZLE_64B, CU_TENSOR_MAP_L2_PROMOTION_L2_128B, CU_TENSOR_MAP_FLOAT_OOB_FILL_NONE);
  }
  {
    cuuint64_t dims[3] = {64, 512, 8}, st[2] = {1024, 128};
    cuuint32_t box[3] = {64, 64, 2};
    enc(&mo, CU_TENSOR_MAP_DATA_TYPE_BFLOAT16, 3, d_in[3], dims, st, box, es, CU_TENSOR_MAP_INTERLEAVE_NONE,
        CU_TENSOR_MAP_SWIZZLE_128B, CU_TENSOR_MAP_L2_PROMOTION_L2_128B, CU_TENSOR_MAP_FLOAT_OOB_FILL_NONE);
  }
  {
    cuuint64_t dims[4] = {512, 4, 16, 32}, st[3] = {16384, 1024, 65536};
    cuuint32_t box[4] = {64, 4, 16, 2};
    enc(&mu, CU_TENSOR_MAP_DATA_TYPE_BFLOAT16, 4, d_in[4], dims, st, box, es, CU_TENSOR_MAP_INTERLEAVE_NONE,
        CU_TENSOR_MAP_SWIZZLE_128B, CU_TENSOR_MAP_L2_PROMOTION_L2_128B, CU_TENSOR_MAP_FLOAT_OOB_FILL_NONE);
  }
  {
    cuuint64_t dims[2] = {1024, 2048}, st[1] = {2048};
    cuuint32_t box[2] = {64, 16};
    enc(&mout, CU_TENSOR_MAP_DATA_TYPE_BFLOAT16, 2, d_out, dims, st, box, es, CU_TENSOR_MAP_INTERLEAVE_NONE,
        CU_TENSOR_MAP_SWIZZLE_128B, CU_TENSOR_MAP_L2_PROMOTION_NONE, CU_TENSOR_MAP_FLOAT_OOB_FILL_NONE);
  }
  {
    cuuint64_t dims[4] = {512, 64, 3, 8}, st[3] = {3072, 1024, 64 * 3072};
    cuuint32_t box[4] = {32, 64, 3, 2};
    enc(&mw4, CU_TENSOR_MAP_DATA_TYPE_BFLOAT16, 4, d_in[1], dims, st, box, es, CU_TENSOR_MAP_INTERLEAVE_NONE,
        CU_TENSOR_MAP_SWIZZLE_64B, CU_TENSOR_MAP_L2_PROMOTION_L2_128B, CU_TENSOR_MAP_FLOAT_OOB_FILL_NONE);
  }
  Params P;
  P.x = (const __nv_bfloat16*)d_in[0];
  P.wphi = (const __nv_bfloat16*)d_in[2];
  P.wo = (const __nv_bfloat16*)d_in[3];
  P.logA = (const __nv_bfloat16*)d_in[5];
  P.Aim = (const __nv_bfloat16*)d_in[6];
  P.Cre = (const __nv_bfloat16*)d_in[7];
  P.Cim = (const __nv_bfloat16*)d_in[8];
  P.logdt = (const __nv_bfloat16*)d_in[9];
  P.Dskip = (const __nv_bfloat16*)d_in[10];
  P.out = (__nv_bfloat16*)d_out;
  cudaGetSymbolAddress((void**)&P.xs, g_x);
  P.ts = nullptr;
  cudaFuncSetAttribute(fused_kernel, cudaFuncAttributeMaxDynamicSharedMemorySize, SMEM_BYTES);
  fused_kernel<<<NCTA, NTHREADS, SMEM_BYTES>>>(P, mx, mw, mo, mu, mout, mw4);
}
```

```cpp
#include <cuda_runtime.h>
#include <cuda_bf16.h>
#include <cuda_fp16.h>
#include <cuda.h>
#include <stdint.h>

#define DBG_TS 0

namespace {

constexpr int NTHREADS = 512;
constexpr int NCTA = 128;
constexpr int OFF_W = 0;
constexpr int OFF_X = 98304;
constexpr int OFF_U = OFF_X + 65536;
constexpr int U_CH = 4416, U_ODD = 2240, U_PAD = 128;
constexpr int OFF_STG0 = OFF_U + 18432;
constexpr int SLAB = 3328;
constexpr int OFF_T = OFF_STG0 + 8 * SLAB;
constexpr int T_CH = 5216;
constexpr int T_D = 0;
constexpr int T_5 = 2144;
constexpr int T_3 = T_5 + 384;
constexpr int T_7 = T_5 + 1024;
constexpr int T_9 = T_7 + 320;
constexpr int T_KC = T_9 + 320;
constexpr int T_ST = T_5 - 1024;
constexpr int OFF_PHI = OFF_T + 4 * T_CH;
constexpr int OFF_EYE = OFF_PHI + 1024, OFF_ONE = OFF_EYE + 512;
constexpr int OFF_BAR = OFF_ONE + 256;
constexpr int SMEM_BYTES = OFF_BAR + 512 + 256 * DBG_TS;
constexpr uint32_t SB = 1024;
static_assert(T_KC + 2 * 656 <= T_CH, "table size");
static_assert(SMEM_BYTES <= 232448, "smem");
constexpr int MB_URAW = 0, MB_FULL = 1  , MB_WO = 17, MB_UFULL = 18, MB_O = 19  ,
              MB_EMPTY = 23  , MB_AUX = 39;
__host__ __device__ constexpr uint32_t BAR(int i) { return SB + OFF_BAR + 8 * i; }
constexpr int NB_WG0 = 1, NB_ODONE = 2, NB_ST0 = 3  , NB_KV = 5, NB_YZ = 6, NB_INIT = 7, NB_PREP = 8, NB_PROD = 9, NB_KREAD = 10, NB_BDONE = 11, NB_GATE = 12,
              NB_Y = 7  ;
#define X2_AT -1
#define GATE_B 2
#define POLL 0
#define GATE_AT 1
#define U_AT 2
#define ZERO_STEP 12
constexpr int SPIN_MAX = 1 << 16;

constexpr int X_CNT = 0;
constexpr int X_PART = 256;
constexpr int X_O = X_PART + 16 * 8 * 144;
constexpr int X_Y = X_O + 32 * 32 * 128;
constexpr int X_UT = X_Y + 512 * 8 * 32;
constexpr int X_SIZE = X_UT + 512 * (U_CH / 16);
__device__ __align__(128) uint4 g_x[X_SIZE];
extern __shared__ uint8_t smem_raw[];
#define TS(i) do {} while (0)
#define TS1(i) do {} while (0)
#define GT(i) do {} while (0)
#define TSDUMP(base) do {} while (0)

__device__ __forceinline__ uint32_t smem_u32(const void* p) { return (uint32_t)__cvta_generic_to_shared(p); }
__device__ __forceinline__ void mbar_arrive(uint32_t b) {
  asm volatile("mbarrier.arrive.shared::cta.b64 _, [%0];" ::"r"(b) : "memory");
}
__device__ __forceinline__ void mbar_wait(uint32_t b) {
  uint32_t done = 0;
#pragma unroll 1
  for (int i = 0; i < SPIN_MAX && !done; i++) {
    asm volatile("{\n.reg .pred p;\nmbarrier.try_wait.parity.shared::cta.b64 p, [%1], 0, 4000;\nselp.u32 %0, 1, 0, p;\n}\n"
                 : "=r"(done) : "r"(b) : "memory");
  }
}
__device__ __forceinline__ void mbar_spin(uint32_t b) {
  uint32_t done = 0;
#pragma unroll 1
  for (int i = 0; i < (SPIN_MAX << 4) && !done; i++) {
    asm volatile("{\n.reg .pred p;\nmbarrier.try_wait.parity.shared::cta.b64 p, [%1], 0;\nselp.u32 %0, 1, 0, p;\n}\n"
                 : "=r"(done) : "r"(b) : "memory");
  }
}
__device__ __forceinline__ void mbar_init(uint32_t b, int n) {
  asm volatile("mbarrier.init.shared::cta.b64 [%0], %1;" ::"r"(b), "r"(n) : "memory");
}
__device__ __forceinline__ void mbar_expect(uint32_t b, int bytes) {
  asm volatile("mbarrier.arrive.expect_tx.shared::cta.b64 _, [%0], %1;" ::"r"(b), "r"(bytes) : "memory");
}
__device__ __forceinline__ void nb_sync(int id, int n) { asm volatile("bar.sync %0, %1;" ::"r"(id), "r"(n) : "memory"); }
__device__ __forceinline__ void nb_arrive(int id, int n) { asm volatile("bar.arrive %0, %1;" ::"r"(id), "r"(n) : "memory"); }
#define ELECT "{\n.reg .pred p;\nelect.sync _|p, 0xffffffff;\n@p "
__device__ __forceinline__ void e_arrive(uint32_t b) {
  asm volatile(ELECT "mbarrier.arrive.shared::cta.b64 _, [%0];\n}\n" ::"r"(b) : "memory");
}
__device__ __forceinline__ void e_expect(uint32_t b, int bytes) {
  asm volatile(ELECT "mbarrier.arrive.expect_tx.shared::cta.b64 _, [%0], %1;\n}\n" ::"r"(b), "r"(bytes) : "memory");
}
__device__ __forceinline__ void e_tma2d(uint32_t dst, const CUtensorMap* m, uint32_t bar, int c0, int c1) {
  asm volatile(ELECT "cp.async.bulk.tensor.2d.shared::cluster.global.mbarrier::complete_tx::bytes [%0], [%1, {%3,%4}], [%2];\n}\n"
               ::"r"(dst), "l"(m), "r"(bar), "r"(c0), "r"(c1) : "memory");
}
__device__ __forceinline__ void e_tma3d(uint32_t dst, const CUtensorMap* m, uint32_t bar, int c0, int c1, int c2) {
  asm volatile(ELECT "cp.async.bulk.tensor.3d.shared::cluster.global.mbarrier::complete_tx::bytes [%0], [%1, {%3,%4,%5}], [%2];\n}\n"
               ::"r"(dst), "l"(m), "r"(bar), "r"(c0), "r"(c1), "r"(c2) : "memory");
}
__device__ __forceinline__ void e_tma4d(uint32_t dst, const CUtensorMap* m, uint32_t bar, int c0, int c3) {
  asm volatile(ELECT "cp.async.bulk.tensor.4d.shared::cluster.global.mbarrier::complete_tx::bytes [%0], [%1, {%3,%5,%5,%4}], [%2];\n}\n"
               ::"r"(dst), "l"(m), "r"(bar), "r"(c0), "r"(c3), "r"(0) : "memory");
}
__device__ __forceinline__ void e_bulk(uint32_t dst, const void* src, int bytes, uint32_t bar) {
  asm volatile(ELECT "cp.async.bulk.shared::cluster.global.mbarrier::complete_tx::bytes [%0], [%1], %2, [%3];\n}\n"
               ::"r"(dst), "l"(src), "r"(bytes), "r"(bar) : "memory");
}
__device__ __forceinline__ void e_prefetch(const void* p, int bytes) {
  asm volatile(ELECT "cp.async.bulk.prefetch.L2.global [%0], %1;\n}\n" ::"l"(p), "r"(bytes) : "memory");
}
__device__ __forceinline__ void e_store2d(const CUtensorMap* m, uint32_t src, int c0, int c1) {
  asm volatile(ELECT "cp.async.bulk.tensor.2d.global.shared::cta.bulk_group [%0, {%2,%3}], [%1];\n}\n"
               ::"l"(m), "r"(src), "r"(c0), "r"(c1) : "memory");
}
__host__ __device__ constexpr uint64_t mkdesc(uint32_t addr, uint32_t lbo, uint32_t sbo, int swz) {
  return (uint64_t)((addr & 0x3FFFF) >> 4) | ((uint64_t)(lbo >> 4) << 16) | ((uint64_t)(sbo >> 4) << 32) |
         ((uint64_t)swz << 62);
}
#define SPLIT() asm volatile("{\n.reg .pred p;\nsetp.eq.u32 p, %0, %1;\n@p exit;\n}\n" ::"r"(blockIdx.y), "n"(__LINE__) : "memory")
#define SPLITN(n) asm volatile("{\n.reg .pred p;\nsetp.eq.u32 p, %0, %1;\n@p exit;\n}\n" ::"r"(blockIdx.y), "r"(4096 + (n)) : "memory")
#define WG_FENCE() asm volatile("wgmma.fence.sync.aligned;" ::: "memory")
#define WG_COMMIT() asm volatile("wgmma.commit_group.sync.aligned;" ::: "memory")
#define WG_WAIT(n) asm volatile("wgmma.wait_group.sync.aligned " #n ";" ::: "memory")

__device__ __forceinline__ void mma(float& d0, float& d1, float& d2, float& d3, uint32_t a0, uint32_t a1, uint32_t a2,
                                    uint32_t a3, uint32_t b0, uint32_t b1) {
  asm volatile("mma.sync.aligned.m16n8k16.row.col.f32.bf16.bf16.f32 {%0,%1,%2,%3},{%4,%5,%6,%7},{%8,%9},{%0,%1,%2,%3};"
               : "+f"(d0), "+f"(d1), "+f"(d2), "+f"(d3)
               : "r"(a0), "r"(a1), "r"(a2), "r"(a3), "r"(b0), "r"(b1));
}
__device__ __forceinline__ void mmac(float (&d)[4], uint32_t a0, uint32_t a1, uint32_t a2, uint32_t a3, uint32_t b0,
                                     uint32_t b1, const float (&c)[4]) {
  asm volatile("mma.sync.aligned.m16n8k16.row.col.f32.bf16.bf16.f32 {%0,%1,%2,%3},{%4,%5,%6,%7},{%8,%9},{%10,%11,%12,%13};"
               : "=f"(d[0]), "=f"(d[1]), "=f"(d[2]), "=f"(d[3])
               : "r"(a0), "r"(a1), "r"(a2), "r"(a3), "r"(b0), "r"(b1), "f"(c[0]), "f"(c[1]), "f"(c[2]), "f"(c[3]));
}
__device__ __forceinline__ void mma_p(int p, float (&d)[4], uint32_t a0, uint32_t a1, uint32_t a2, uint32_t a3, uint32_t b0, uint32_t b1) {
  asm volatile("{\n.reg .pred q;\nsetp.ne.b32 q, %10, 0;\n"
               "@q mma.sync.aligned.m16n8k16.row.col.f32.bf16.bf16.f32 {%0,%1,%2,%3},{%4,%5,%6,%7},{%8,%9},{%0,%1,%2,%3};\n}\n"
               : "+f"(d[0]), "+f"(d[1]), "+f"(d[2]), "+f"(d[3])
               : "r"(a0), "r"(a1), "r"(a2), "r"(a3), "r"(b0), "r"(b1), "r"(p));
}
__device__ __forceinline__ void mmac_p(int p, float (&d)[4], uint32_t a0, uint32_t a1, uint32_t a2, uint32_t a3, uint32_t b0,
                                       uint32_t b1, const float (&c)[4]) {
  asm volatile("{\n.reg .pred q;\nsetp.ne.b32 q, %14, 0;\n"
               "@q mma.sync.aligned.m16n8k16.row.col.f32.bf16.bf16.f32 {%0,%1,%2,%3},{%4,%5,%6,%7},{%8,%9},{%10,%11,%12,%13};\n}\n"
               : "+f"(d[0]), "+f"(d[1]), "+f"(d[2]), "+f"(d[3])
               : "r"(a0), "r"(a1), "r"(a2), "r"(a3), "r"(b0), "r"(b1), "f"(c[0]), "f"(c[1]), "f"(c[2]), "f"(c[3]), "r"(p));
}
__device__ __forceinline__ void mma_h(float (&d)[4], const uint32_t (&a)[4], uint32_t b0, uint32_t b1) {
  asm volatile("mma.sync.aligned.m16n8k16.row.col.f32.f16.f16.f32 {%0,%1,%2,%3},{%4,%5,%6,%7},{%8,%9},{%0,%1,%2,%3};"
               : "+f"(d[0]), "+f"(d[1]), "+f"(d[2]), "+f"(d[3]) : "r"(a[0]), "r"(a[1]), "r"(a[2]), "r"(a[3]), "r"(b0), "r"(b1));
}
__device__ __forceinline__ void mma0(float& d0, float& d1, float& d2, float& d3, uint32_t a0, uint32_t a1, uint32_t a2,
                                     uint32_t a3, uint32_t b0, uint32_t b1) {
  asm volatile("mma.sync.aligned.m16n8k16.row.col.f32.bf16.bf16.f32 {%0,%1,%2,%3},{%4,%5,%6,%7},{%8,%9},{%10,%10,%10,%10};"
               : "=f"(d0), "=f"(d1), "=f"(d2), "=f"(d3)
               : "r"(a0), "r"(a1), "r"(a2), "r"(a3), "r"(b0), "r"(b1), "f"(0.f));
}
__device__ __forceinline__ uint32_t pack_bf(float lo, float hi) {
  uint32_t r;
  asm("cvt.rn.bf16x2.f32 %0, %1, %2;" : "=r"(r) : "f"(hi), "f"(lo));
  return r;
}
__device__ __forceinline__ float bf_lo(uint32_t w) { return __uint_as_float(w << 16); }
__device__ __forceinline__ float bf_hi(uint32_t w) { return __uint_as_float(w & 0xffff0000u); }
__device__ __forceinline__ float bf_round(float x) { return __bfloat162float(__float2bfloat16_rn(x)); }
__device__ __forceinline__ uint32_t bmax2(uint32_t a, uint32_t b) {
  uint32_t r; asm("max.bf16x2 %0, %1, %2;" : "=r"(r) : "r"(a), "r"(b)); return r;
}
__device__ __forceinline__ uint32_t bmin2(uint32_t a, uint32_t b) {
  uint32_t r; asm("min.bf16x2 %0, %1, %2;" : "=r"(r) : "r"(a), "r"(b)); return r;
}
__device__ __forceinline__ float ex2(float x) { float r; asm("ex2.approx.ftz.f32 %0, %1;" : "=f"(r) : "f"(x)); return r; }
__device__ __forceinline__ float rcp(float x) { float r; asm("rcp.approx.ftz.f32 %0, %1;" : "=f"(r) : "f"(x)); return r; }
__device__ __forceinline__ void ldsm4(uint32_t (&r)[4], uint32_t a) {
  asm volatile("ldmatrix.sync.aligned.m8n8.x4.shared.b16 {%0,%1,%2,%3}, [%4];"
               : "=r"(r[0]), "=r"(r[1]), "=r"(r[2]), "=r"(r[3]) : "r"(a) : "memory");
}
__device__ __forceinline__ void ldsm4t(uint32_t (&r)[4], uint32_t a) {
  asm volatile("ldmatrix.sync.aligned.m8n8.x4.trans.shared.b16 {%0,%1,%2,%3}, [%4];"
               : "=r"(r[0]), "=r"(r[1]), "=r"(r[2]), "=r"(r[3]) : "r"(a) : "memory");
}
__device__ __forceinline__ void stsm4(uint32_t a, uint32_t r0, uint32_t r1, uint32_t r2, uint32_t r3) {
  asm volatile("stmatrix.sync.aligned.m8n8.x4.shared.b16 [%0], {%1,%2,%3,%4};"
               ::"r"(a), "r"(r0), "r"(r1), "r"(r2), "r"(r3) : "memory");
}
__device__ __forceinline__ uint32_t lds32(uint32_t a) {
  uint32_t r; asm volatile("ld.shared.u32 %0, [%1];" : "=r"(r) : "r"(a) : "memory"); return r;
}
__device__ __forceinline__ uint32_t lds16(uint32_t a) {
  uint32_t r; asm volatile("{\n.reg .u16 h;\nld.shared.u16 h, [%1];\ncvt.u32.u16 %0, h;\n}\n" : "=r"(r) : "r"(a) : "memory"); return r;
}
__device__ __forceinline__ uint2 lds64(uint32_t a) {
  uint2 r; asm volatile("ld.shared.v2.u32 {%0,%1}, [%2];" : "=r"(r.x), "=r"(r.y) : "r"(a) : "memory"); return r;
}
__device__ __forceinline__ uint4 lds128(uint32_t a) {
  uint4 r;
  asm volatile("ld.shared.v4.u32 {%0,%1,%2,%3}, [%4];" : "=r"(r.x), "=r"(r.y), "=r"(r.z), "=r"(r.w) : "r"(a) : "memory");
  return r;
}
__device__ __forceinline__ void sts32(uint32_t a, uint32_t v) { asm volatile("st.shared.u32 [%0], %1;" ::"r"(a), "r"(v) : "memory"); }
__device__ __forceinline__ void sts16(uint32_t a, uint32_t v) {
  asm volatile("{\n.reg .u16 h;\ncvt.u16.u32 h, %1;\nst.shared.u16 [%0], h;\n}\n" ::"r"(a), "r"(v) : "memory");
}
__device__ __forceinline__ void sts64(uint32_t a, uint32_t x, uint32_t y) {
  asm volatile("st.shared.v2.u32 [%0], {%1,%2};" ::"r"(a), "r"(x), "r"(y) : "memory");
}
__device__ __forceinline__ void sts128(uint32_t a, uint32_t x, uint32_t y, uint32_t z, uint32_t w) {
  asm volatile("st.shared.v4.u32 [%0], {%1,%2,%3,%4};" ::"r"(a), "r"(x), "r"(y), "r"(z), "r"(w) : "memory");
}
__device__ __forceinline__ uint4 ld_x(const uint4* p) {
  uint4 r;
  asm volatile("{\n.reg .b128 t;\nld.relaxed.gpu.global.b128 t, [%4];\nmov.b128 {%0,%1,%2,%3}, t;\n}\n"
               : "=r"(r.x), "=r"(r.y), "=r"(r.z), "=r"(r.w) : "l"(p) : "memory");
  return r;
}
__device__ __forceinline__ uint32_t ld_x32(const uint32_t* p) {
  uint32_t r; asm volatile("ld.relaxed.gpu.global.u32 %0, [%1];" : "=r"(r) : "l"(p) : "memory"); return r;
}
__device__ __forceinline__ void st_x(uint4* p, uint32_t x, uint32_t y, uint32_t z, uint32_t w) {
  asm volatile("{\n.reg .b128 t;\nmov.b128 t, {%1,%2,%3,%4};\nst.relaxed.gpu.global.b128 [%0], t;\n}\n"
               ::"l"(p), "r"(x), "r"(y), "r"(z), "r"(w) : "memory");
}
__device__ __forceinline__ void st_x_p(int p, uint4* a, uint32_t x, uint32_t y, uint32_t z, uint32_t w) {
  asm volatile("{\n.reg .b128 t;\n.reg .pred q;\nsetp.ne.b32 q, %5, 0;\nmov.b128 t, {%1,%2,%3,%4};\n@q st.relaxed.gpu.global.b128 [%0], t;\n}\n"
               ::"l"(a), "r"(x), "r"(y), "r"(z), "r"(w), "r"(p) : "memory");
}
__device__ __forceinline__ void sts64_p(int p, uint32_t a, uint32_t x, uint32_t y) {
  asm volatile("{\n.reg .pred q;\nsetp.ne.b32 q, %3, 0;\n@q st.shared.v2.u32 [%0], {%1,%2};\n}\n" ::"r"(a), "r"(x), "r"(y), "r"(p) : "memory");
}
__device__ __forceinline__ void st_x32(uint32_t* p, uint32_t x) {
  asm volatile("st.relaxed.gpu.global.u32 [%0], %1;" ::"l"(p), "r"(x) : "memory");
}
__device__ __forceinline__ uint32_t nz(uint32_t w) { return max(w, 1u); }
__device__ __forceinline__ uint32_t fu(float x) { return __float_as_uint(x); }
__device__ __forceinline__ float uf(uint32_t x) { return __uint_as_float(x); }

__device__ __forceinline__ void wgmma_ss_n96(float (&d)[48], uint64_t da, uint64_t db, int sc) {
  asm volatile("{\n.reg .pred p;\nsetp.ne.b32 p, %50, 0;\n"
      "wgmma.mma_async.sync.aligned.m64n96k16.f32.bf16.bf16 "
      "{%0,%1,%2,%3,%4,%5,%6,%7,%8,%9,%10,%11,%12,%13,%14,%15,%16,%17,%18,%19,%20,%21,%22,%23,%24,%25,%26,%27,%28,%29,%30,%31,%32,%33,%34,%35,%36,%37,%38,%39,%40,%41,%42,%43,%44,%45,%46,%47}, "
      "%48, %49, p, 1, 1, 0, 1;\n}\n"
      : "+f"(d[0]), "+f"(d[1]), "+f"(d[2]), "+f"(d[3]), "+f"(d[4]), "+f"(d[5]), "+f"(d[6]), "+f"(d[7]),
        "+f"(d[8]), "+f"(d[9]), "+f"(d[10]), "+f"(d[11]), "+f"(d[12]), "+f"(d[13]), "+f"(d[14]), "+f"(d[15]),
        "+f"(d[16]), "+f"(d[17]), "+f"(d[18]), "+f"(d[19]), "+f"(d[20]), "+f"(d[21]), "+f"(d[22]), "+f"(d[23]),
        "+f"(d[24]), "+f"(d[25]), "+f"(d[26]), "+f"(d[27]), "+f"(d[28]), "+f"(d[29]), "+f"(d[30]), "+f"(d[31]),
        "+f"(d[32]), "+f"(d[33]), "+f"(d[34]), "+f"(d[35]), "+f"(d[36]), "+f"(d[37]), "+f"(d[38]), "+f"(d[39]),
        "+f"(d[40]), "+f"(d[41]), "+f"(d[42]), "+f"(d[43]), "+f"(d[44]), "+f"(d[45]), "+f"(d[46]), "+f"(d[47])
      : "l"(da), "l"(db), "r"(sc));
}

__device__ __forceinline__ void wgmma_ss_n128(float (&d)[64], uint64_t da, uint64_t db, int sc) {
  asm volatile("{\n.reg .pred p;\nsetp.ne.b32 p, %66, 0;\n"
      "wgmma.mma_async.sync.aligned.m64n128k16.f32.bf16.bf16 "
      "{%0,%1,%2,%3,%4,%5,%6,%7,%8,%9,%10,%11,%12,%13,%14,%15,%16,%17,%18,%19,%20,%21,%22,%23,%24,%25,%26,%27,%28,%29,%30,%31,%32,%33,%34,%35,%36,%37,%38,%39,%40,%41,%42,%43,%44,%45,%46,%47,%48,%49,%50,%51,%52,%53,%54,%55,%56,%57,%58,%59,%60,%61,%62,%63}, "
      "%64, %65, p, 1, 1, 0, 1;\n}\n"
      : "+f"(d[0]), "+f"(d[1]), "+f"(d[2]), "+f"(d[3]), "+f"(d[4]), "+f"(d[5]), "+f"(d[6]), "+f"(d[7]),
        "+f"(d[8]), "+f"(d[9]), "+f"(d[10]), "+f"(d[11]), "+f"(d[12]), "+f"(d[13]), "+f"(d[14]), "+f"(d[15]),
        "+f"(d[16]), "+f"(d[17]), "+f"(d[18]), "+f"(d[19]), "+f"(d[20]), "+f"(d[21]), "+f"(d[22]), "+f"(d[23]),
        "+f"(d[24]), "+f"(d[25]), "+f"(d[26]), "+f"(d[27]), "+f"(d[28]), "+f"(d[29]), "+f"(d[30]), "+f"(d[31]),
        "+f"(d[32]), "+f"(d[33]), "+f"(d[34]), "+f"(d[35]), "+f"(d[36]), "+f"(d[37]), "+f"(d[38]), "+f"(d[39]),
        "+f"(d[40]), "+f"(d[41]), "+f"(d[42]), "+f"(d[43]), "+f"(d[44]), "+f"(d[45]), "+f"(d[46]), "+f"(d[47]),
        "+f"(d[48]), "+f"(d[49]), "+f"(d[50]), "+f"(d[51]), "+f"(d[52]), "+f"(d[53]), "+f"(d[54]), "+f"(d[55]),
        "+f"(d[56]), "+f"(d[57]), "+f"(d[58]), "+f"(d[59]), "+f"(d[60]), "+f"(d[61]), "+f"(d[62]), "+f"(d[63])
      : "l"(da), "l"(db), "r"(sc));
}

__device__ __forceinline__ void wgmma_ss_n40(float (&d)[20], uint64_t da, uint64_t db, int sc) {
  asm volatile("{\n.reg .pred p;\nsetp.ne.b32 p, %22, 0;\n"
      "wgmma.mma_async.sync.aligned.m64n40k16.f32.bf16.bf16 "
      "{%0,%1,%2,%3,%4,%5,%6,%7,%8,%9,%10,%11,%12,%13,%14,%15,%16,%17,%18,%19}, "
      "%20, %21, p, 1, 1, 1, 1;\n}\n"
      : "+f"(d[0]), "+f"(d[1]), "+f"(d[2]), "+f"(d[3]), "+f"(d[4]), "+f"(d[5]), "+f"(d[6]), "+f"(d[7]),
        "+f"(d[8]), "+f"(d[9]), "+f"(d[10]), "+f"(d[11]), "+f"(d[12]), "+f"(d[13]), "+f"(d[14]), "+f"(d[15]),
        "+f"(d[16]), "+f"(d[17]), "+f"(d[18]), "+f"(d[19])
      : "l"(da), "l"(db), "r"(sc));
}

__device__ __forceinline__ void wgmma_rs_n8(float (&d)[4], const uint4& a, uint64_t db, int sc) {
  asm volatile("{\n.reg .pred p;\nsetp.ne.b32 p, %9, 0;\n"
      "wgmma.mma_async.sync.aligned.m64n8k16.f32.bf16.bf16 "
      "{%0,%1,%2,%3}, "
      "{%4,%5,%6,%7}, %8, p, 1, 1, 1;\n}\n"
      : "+f"(d[0]), "+f"(d[1]), "+f"(d[2]), "+f"(d[3])
      : "r"(a.x), "r"(a.y), "r"(a.z), "r"(a.w), "l"(db), "r"(sc));
}

__device__ __forceinline__ void wgmma_rs_n16(float (&d)[8], const uint4& a, uint64_t db, int sc) {
  asm volatile("{\n.reg .pred p;\nsetp.ne.b32 p, %13, 0;\n"
      "wgmma.mma_async.sync.aligned.m64n16k16.f32.bf16.bf16 "
      "{%0,%1,%2,%3,%4,%5,%6,%7}, "
      "{%8,%9,%10,%11}, %12, p, 1, 1, 1;\n}\n"
      : "+f"(d[0]), "+f"(d[1]), "+f"(d[2]), "+f"(d[3]), "+f"(d[4]), "+f"(d[5]), "+f"(d[6]), "+f"(d[7])
      : "r"(a.x), "r"(a.y), "r"(a.z), "r"(a.w), "l"(db), "r"(sc));
}

__device__ __forceinline__ void wgmma_rs_n24(float (&d)[12], const uint4& a, uint64_t db, int sc) {
  asm volatile("{\n.reg .pred p;\nsetp.ne.b32 p, %17, 0;\n"
      "wgmma.mma_async.sync.aligned.m64n24k16.f32.bf16.bf16 "
      "{%0,%1,%2,%3,%4,%5,%6,%7,%8,%9,%10,%11}, "
      "{%12,%13,%14,%15}, %16, p, 1, 1, 1;\n}\n"
      : "+f"(d[0]), "+f"(d[1]), "+f"(d[2]), "+f"(d[3]), "+f"(d[4]), "+f"(d[5]), "+f"(d[6]), "+f"(d[7]),
        "+f"(d[8]), "+f"(d[9]), "+f"(d[10]), "+f"(d[11])
      : "r"(a.x), "r"(a.y), "r"(a.z), "r"(a.w), "l"(db), "r"(sc));
}

struct Params {
  const __nv_bfloat16 *logA, *Aim, *Cre, *Cim, *logdt, *Dskip, *x, *wphi, *wo;
  __nv_bfloat16* out;
  uint4* xs;
  long long* ts;
};

__device__ __forceinline__ uint4 tr_row(const uint4 (&v)[8], int i) {
  uint32_t o[4];
#pragma unroll
  for (int m = 0; m < 4; m++) {
    const uint4 &ra = v[2 * m], &rb = v[2 * m + 1];
    const int k = i >> 1;
    const uint32_t xa = k == 0 ? ra.x : k == 1 ? ra.y : k == 2 ? ra.z : ra.w;
    const uint32_t xb = k == 0 ? rb.x : k == 1 ? rb.y : k == 2 ? rb.z : rb.w;
    o[m] = __byte_perm(xa, xb, (i & 1) ? 0x7632 : 0x5410);
  }
  return make_uint4(o[0], o[1], o[2], o[3]);
}

struct cpx { float r, i; };
__device__ __forceinline__ cpx csq(cpx a) { return {a.r * a.r - a.i * a.i, 2.f * (a.r * a.i)}; }
__device__ __forceinline__ cpx polar(float e, float t) {
  const float m = ex2(e);
  return {m * __cosf(t), m * __sinf(t)};
}

struct KgenRaw { uint32_t la, ai, cr, ci; unsigned short ldt; };
__device__ __forceinline__ KgenRaw kgen_load(const Params& P, int d, int unit, int lane) {
  const int o = d * 64 + unit * 32 + lane;
  return {__ldg((const uint32_t*)P.logA + o), __ldg((const uint32_t*)P.Aim + o), __ldg((const uint32_t*)P.Cre + o),
          __ldg((const uint32_t*)P.Cim + o), __ldg((const unsigned short*)P.logdt + d)};
}
struct hc { __half2 r, i; };
struct cpx2 { cpx a, b; };
__device__ __forceinline__ cpx2 csq2(const cpx2& v) { return {csq(v.a), csq(v.b)}; }
__device__ __forceinline__ hc toh(const cpx2& v) { return {__floats2half2_rn(v.a.r, v.b.r), __floats2half2_rn(v.a.i, v.b.i)}; }
__device__ __forceinline__ hc hmul(const hc& z, const hc& w) {
  return {__hfma2(z.r, w.r, __hneg2(__hmul2(z.i, w.i))), __hfma2(z.r, w.i, __hmul2(z.i, w.r))};
}
__device__ __forceinline__ hc hmulc(const hc& z, const hc& w) {
  return {__hfma2(z.r, w.r, __hmul2(z.i, w.i)), __hfma2(z.i, w.r, __hneg2(__hmul2(z.r, w.i)))};
}
__device__ __forceinline__ uint32_t hu(__half2 v) { return *(const uint32_t*)&v; }
__device__ __forceinline__ __half2 uh(uint32_t v) { return *(const __half2*)&v; }

struct KgenAddr { uint32_t sa, lb, lm[4]; };
__device__ __forceinline__ KgenAddr kgen_addr(int lane, uint32_t buf) {
  KgenAddr a;
  a.sa = buf + (lane & 7) * 128 + ((((lane >> 3) ^ lane) & 7) << 4);
  const int q = lane >> 4;
  const uint32_t b = buf + ((lane >> 3) & 1) * 1024 + q * 128;
  a.lb = b + (((lane ^ q) & 7) << 4);
  a.lm[0] = b + (q << 4);
  a.lm[1] = b + ((1 ^ q) << 4);
  a.lm[2] = b + (((2 + (lane & 1)) ^ q) << 4);
  a.lm[3] = b + (((4 + (lane & 3)) ^ q) << 4);
  asm volatile("" : "+r"(a.sa), "+r"(a.lb), "+r"(a.lm[0]), "+r"(a.lm[1]), "+r"(a.lm[2]), "+r"(a.lm[3]));
  return a;
}
__device__ __forceinline__ void kgen_unit(const KgenRaw& r, const KgenAddr& ad, uint32_t zero, float (&k)[5][4], float& k2048, float& sc) {
  const float dt = bf_round(expf(bf_lo(r.ldt)));
  const uint32_t ar = pack_bf(ex2(bf_lo(r.la) * 1.4426950408889634f), ex2(bf_hi(r.la) * 1.4426950408889634f));
  const float ca = dt * -1.4426950408889634f, a0 = bf_lo(ar) * ca, a1 = bf_hi(ar) * ca;
  const float f0 = bf_lo(r.ai) * dt, f1 = bf_hi(r.ai) * dt;
  const float r0 = f0 * 20.21267777267071f, r1 = f1 * 20.21267777267071f;
  const uint32_t cm = __vmaxu2(r.cr & 0x7fff7fffu, r.ci & 0x7fff7fffu);
  const uint32_t ex = min(max(__reduce_max_sync(0xffffffffu, max(cm >> 16, cm & 0xffffu)) >> 7, 1u), 253u);
  const float cs = uf((254u - ex) << 23);
  sc = 2.f * dt * uf(ex << 23);
  const cpx2 C = {{bf_lo(r.cr) * cs, bf_lo(r.ci) * -cs}, {bf_hi(r.cr) * cs, bf_hi(r.ci) * -cs}};
  auto put = [&](const hc (&v)[8]) {
    stsm4(ad.sa, hu(v[0].r), hu(v[1].r), hu(v[2].r), hu(v[3].r));
    stsm4(ad.sa + 1024, hu(v[0].i), hu(v[1].i), hu(v[2].i), hu(v[3].i));
    stsm4(ad.sa ^ 64, hu(v[4].r), hu(v[5].r), hu(v[6].r), hu(v[7].r));
    stsm4((ad.sa ^ 64) + 1024, hu(v[4].i), hu(v[5].i), hu(v[6].i), hu(v[7].i));
    __syncwarp();
  };
  auto get = [&](uint32_t (&o)[4][4], uint32_t a) {
#pragma unroll
    for (int i = 0; i < 4; i++) ldsm4(o[i], (a ^ (i << 5)) + i * 256);
  };
  auto at = [](const uint32_t (&o)[4][4], int s) { return hc{uh(o[s >> 1][2 * (s & 1)]), uh(o[s >> 1][2 * (s & 1) + 1])}; };
  uint32_t A[8][4];
  auto tile = [&](int j, const uint32_t (&B)[4][4]) {
    k[j][0] = k[j][1] = k[j][2] = k[j][3] = 0.f;
#pragma unroll
    for (int s = 0; s < 8; s++) mma_h(k[j], A[s], B[s >> 1][2 * (s & 1)], B[s >> 1][2 * (s & 1) + 1]);
  };
  auto after = [&](cpx2 v, uint32_t dep) { v.a.r = uf(fu(v.a.r) ^ (dep & zero)); v.b.r = uf(fu(v.b.r) ^ (dep & zero)); return v; };
  const cpx2 w1 = {polar(a0, f0), polar(a1, f1)};
  const cpx2 w127 = {polar(a0 * 127.f, (r0 - rintf(r0)) * 6.283185307179586f), polar(a1 * 127.f, (r1 - rintf(r1)) * 6.283185307179586f)};
  const cpx2 w2 = csq2(w1), w4 = csq2(w2);
  uint32_t T0[4][4], X[4][4], M[3][4][4];
  {
    hc t[8];
    t[0] = {uh(0x3C003C00u), uh(0u)}; t[1] = toh(w1); t[2] = toh(w2); t[4] = toh(w4);
    t[3] = hmul(t[1], t[2]); t[5] = hmul(t[1], t[4]); t[6] = hmul(t[2], t[4]); t[7] = hmul(t[3], t[4]);
    put(t); get(T0, ad.lb);
  }
  const cpx2 w8 = csq2(w4), w16 = csq2(w8), w32 = csq2(w16), w64 = csq2(w32);
  {
    const hc m8 = toh(w8), m16 = toh(w16), m32 = toh(w32);
    hc a[8];
    a[0] = toh(C); a[1] = hmulc(a[0], m8);
    a[2] = hmulc(a[0], m16); a[3] = hmulc(a[1], m16);
#pragma unroll
    for (int i = 0; i < 4; i++) a[4 + i] = hmulc(a[i], m32);
    put(a); get(X, ad.lb);
  }
  const cpx2 w127b = after(w127, T0[0][0]);
  const cpx2 w128 = {{w127b.a.r * w1.a.r - w127b.a.i * w1.a.i, w127b.a.r * w1.a.i + w127b.a.i * w1.a.r},
                     {w127b.b.r * w1.b.r - w127b.b.i * w1.b.i, w127b.b.r * w1.b.i + w127b.b.i * w1.b.r}};
  const cpx2 w256 = csq2(w128), w512 = csq2(w256);
  const hc m128 = toh(w128), m256 = toh(w256), m512 = toh(w512);
  {
    const hc m254 = toh(csq2(w127b)), m127 = toh(w127b);
    hc m[8];
    m[0] = toh(w64); m[1] = m128; m[2] = m256; m[3] = hmul(m127, m256);
    m[4] = m512; m[5] = hmul(m127, m512); m[6] = hmul(m[4], m254); m[7] = hmul(m[5], m254);
    put(m);
    get(M[0], ad.lm[0]);
#pragma unroll
    for (int s = 0; s < 8; s++) {
      const hc z = at(X, s), y = hmulc(z, at(M[0], s));
      A[s][0] = hu(z.r) + zero; A[s][1] = hu(y.r); A[s][2] = hu(z.i) + zero; A[s][3] = hu(y.i);
    }
#pragma unroll
    for (int i = 0; i < 3; i++) get(M[i], ad.lm[i + 1]);
  }
  tile(0, T0);
  const cpx2 w1024 = csq2(after(w512, X[0][0])), we = csq2(w1024);
  {
    hc t[8];
    t[0] = toh(w1024); t[1] = hmul(t[0], m128);
    t[2] = hmul(t[0], m256); t[3] = hmul(t[1], m256);
#pragma unroll
    for (int i = 0; i < 4; i++) t[4 + i] = hmul(t[i], m512);
    put(t); get(X, ad.lb);
  }
  k2048 = (C.a.r * we.a.r + C.a.i * we.a.i + C.b.r * we.b.r + C.b.i * we.b.i) * sc;
#pragma unroll
  for (int j = 0; j < 3; j++) {
#pragma unroll
    for (int s = 0; s < 8; s++) {
      const hc y = hmul(at(T0, s), at(M[j], s));
      M[j][s >> 1][2 * (s & 1)] = hu(y.r); M[j][s >> 1][2 * (s & 1) + 1] = hu(y.i);
    }
    tile(1 + j, M[j]);
  }
  tile(4, X);
}

__device__ __forceinline__ void build_tables(uint32_t tb, int lane, float (&k)[5][4], float k2048) {
  const int g = lane >> 2, c = lane & 3;
  const uint32_t kc = tb + T_KC + 16;
  {
    const uint32_t a0 = kc + 16 * g + 4 * c, a2 = kc + 2 * (256 + 4 * g + c);
    const uint32_t a3 = kc + 2 * (384 + 2 * g + 64 * (c & 1) + (c >> 1)), a4 = kc + 2 * (512 + g + 32 * c);
#pragma unroll
    for (int r = 0; r < 2; r++) {
      sts32(a0 + 128 * r, pack_bf(k[0][2 * r], k[0][2 * r + 1]));
      sts32(a0 + 128 * r + 256, pack_bf(k[1][2 * r], k[1][2 * r + 1]));
      const uint32_t w2 = pack_bf(k[2][2 * r], k[2][2 * r + 1]);
      const uint32_t w3 = pack_bf(k[3][2 * r], k[3][2 * r + 1]);
      const uint32_t w4 = pack_bf(k[4][2 * r], k[4][2 * r + 1]);
      sts16(a2 + 64 * r, w2); sts16(a2 + 64 * r + 128, w2 >> 16);
      sts16(a3 + 32 * r, w3); sts16(a3 + 32 * r + 64, w3 >> 16);
      sts16(a4 + 16 * r, w4); sts16(a4 + 16 * r + 32, w4 >> 16);
    }
  }
  if (lane == 0) { sts16(kc + 2 * 640, pack_bf(k2048, 0.f)); sts32(kc - 4, 0); }
  __syncwarp();
  const uint32_t td = tb + T_D + 32;
#pragma unroll
  for (int hf = 0; hf < 2; hf++) {
    const uint2 v = lds64(kc + 256 * hf + 8 * lane);
    const uint32_t pv = lds32(kc + 256 * hf + 8 * lane - 4);
    sts128(td + 512 * hf + 16 * lane, __byte_perm(v.x, pv, 0x7610), __byte_perm(v.x, v.x, 0x1032), __byte_perm(v.y, v.x, 0x7610),
           __byte_perm(v.y, v.y, 0x1032));
  }
#pragma unroll
  for (int hf = 0; hf < 2; hf++) {
    const uint32_t v = lds32(kc + 512 + 128 * hf + 4 * lane), nx = lds32(kc + 516 + 128 * hf + 4 * lane);
    uint32_t w0 = __byte_perm(v, v, 0x1010);
    const uint32_t w1 = w0;
    if (hf == 0) { const uint32_t pv = lds32(kc + 508); if (lane == 0) w0 = __byte_perm(v, pv, 0x7610); }
    sts128(td + 1024 + 512 * hf + 16 * lane, w0, w1, __byte_perm(v, v, 0x1032), __byte_perm(nx, v, 0x7610));
  }
  {
    const uint32_t kk = lds16(kc + 2 * 384);
    const uint32_t w = lane < 3 ? (kk | (kk << 16)) : (lane == 3 ? (kk << 16) : 0u);
    if (lane < 24) sts32(td + 4 * (lane < 16 ? 512 + lane : lane - 24), w);
    const uint32_t lo_ = lds16(kc + 2 * 511), le_ = lds16(kc + 2 * 512);
    const uint32_t ja = tb + T_5 + (lane < 16 ? 4 * lane : 256 + 4 * lane);
    sts32(ja, lane == 16 ? (le_ << 16) : 0u);
    sts32(ja + 384, lane == 16 ? (lo_ << 16) : 0u);
    sts32(tb + (lane < 16 ? T_7 : T_9 - 64) + 4 * lane, 0u);
  }
#pragma unroll
  for (int s = 0; s < 2; s++) {
    const uint32_t b = kc + 2 * (s ? 512 : 384) + 8 * lane;
    const uint2 v = lds64(b);
    uint32_t em = lds16(b - 2), e0 = v.x;
    const uint32_t e4 = lds16(b + 8);
    if (lane == 0) { em = 0; e0 = 0; }
    sts64(tb + (s ? T_7 : T_3) + 64 + 8 * lane, __byte_perm(v.x, em, 0x5432), __byte_perm(v.y, v.x, 0x7632));
    sts64(tb + (s ? T_9 : T_5) + 64 + 8 * lane, __byte_perm(v.y, e0, 0x5410), __byte_perm(e4, v.y, 0x5410));
  }
  __syncwarp();
}

__device__ __forceinline__ uint32_t box2w(int lo, int n, int o) {
  return ((unsigned)(o - lo) < (unsigned)n ? 0x3F80u : 0u) | ((unsigned)(o + 1 - lo) < (unsigned)n ? 0x3F800000u : 0u);
}

__device__ __forceinline__ void conv_channel(uint32_t ub, uint32_t tb, int lane, uint4* ydst) {
  const int g = lane >> 2, c = lane & 3, x = g - 2 * c;
  const int mi = lane >> 3;
  const uint32_t qa = ub + U_PAD + 16 * (lane & 7) + ((mi == 0 || mi == 3) ? U_ODD : 0) - (mi == 0 ? 16 : 0);
  const uint32_t hb = ub + U_PAD + (mi & 1) * U_ODD + 16 * ((lane >> 4) + (lane & 7)) - 16;
  const uint32_t kv = lds16(tb + T_KC + 16 + 2 * 512);
  const int oh = c < 2 ? 8 + 2 * c : 2 * c - 8, og = c < 3 ? 2 * c : -10;
  uint32_t bx[4] = {box2w(g - 4, 9, 2 * c), box2w(g - 3, 7, 2 * c), box2w(g - 4, 9, oh), box2w(g - 3, 7, oh)};
  uint32_t by[4] = {box2w(g - 10, 5, 2 * c - 8), box2w(g - 5, 3, 2 * c - 8), box2w(g - 10, 5, og), box2w(g - 5, 3, og)};
  uint32_t lb0 = ((unsigned)(x + 5) < 2u ? kv : 0u) | ((unsigned)(x + 4) < 2u ? kv << 16 : 0u);
  uint32_t lb1 = ((unsigned)(x - 3) < 2u ? kv : 0u) | ((unsigned)(x - 4) < 2u ? kv << 16 : 0u);
  const int q0 = g - 1, q1 = c < 3 ? g : g - 2;
  uint32_t y0a = ub + U_PAD + (q0 & 1) * U_ODD + 16 * (q0 >> 1) + 4 * c;
  uint32_t y1a = ub + U_PAD + (q1 & 1) * U_ODD + 16 * (q1 >> 1) + 4 * c;
#pragma unroll
  for (int i = 0; i < 4; i++) asm volatile("" : "+r"(bx[i]), "+r"(by[i]));
  asm volatile("" : "+r"(lb0), "+r"(lb1), "+r"(y0a), "+r"(y1a));
  mbar_wait(BAR(MB_UFULL));
  mbar_spin(BAR(MB_EMPTY + 15));
  TS(36);
  float acc[16][4];
  {
    uint32_t z09[8], z07[8], zm9[8], zm7[8];
#pragma unroll
    for (int i = 0; i < 8; i++) {
      uint32_t h[4];
      ldsm4(h, hb + 128 * i);
      float y0, y1, y2, y3, w0, w1, w2, w3;
      mma0(y0, y1, y2, y3, bx[0], bx[1], bx[2], bx[3], h[2], c < 2 ? h[3] : h[1]);
      mma0(w0, w1, w2, w3, bx[0], bx[1], bx[2], bx[3], h[1], c < 2 ? h[2] : h[0]);
      z09[i] = pack_bf(y0, y1); z07[i] = pack_bf(y2, y3);
      zm9[i] = pack_bf(w0, w1); zm7[i] = pack_bf(w2, w3);
    }
  uint32_t f3[3][4][4];
  {
    const uint32_t fa = tb + T_7 + 4 * (16 + x);
#pragma unroll
    for (int tt = 0; tt < 3; tt++)
#pragma unroll
      for (int D = 0; D < 4; D++) {
        const uint32_t a = fa + (tt == 0 ? 316 : (tt == 1 ? 320 : 0)) + 64 * D;
        f3[tt][D][0] = lds32(a); f3[tt][D][1] = lds32(a + 32); f3[tt][D][2] = lds32(a - 32); f3[tt][D][3] = lds32(a);
      }
  }
    SPLIT();
    nb_sync(NB_GATE, 256);
    SPLIT();
    float a[4][2][4];
#pragma unroll
    for (int kap = 0; kap < 4; kap++)
#pragma unroll
      for (int sg = 0; sg < 2; sg++)
#pragma unroll
        for (int bk = 3; bk >= kap; bk--) {
          const uint32_t(&q0_)[4] = f3[sg ? 2 : 0][bk - kap];
          const uint32_t(&q1_)[4] = f3[sg ? 2 : 1][bk - kap];
          float(&a0)[4] = a[bk][0];
          float(&a1)[4] = a[bk][1];
          if (sg == 0 && kap == 0) {
            mma0(a0[0], a0[1], a0[2], a0[3], q0_[0], q0_[1], q0_[2], q0_[3], z09[0], z09[1]);
            mma0(a1[0], a1[1], a1[2], a1[3], q1_[0], q1_[1], q1_[2], q1_[3], zm9[0], zm9[1]);
          } else {
            mma(a0[0], a0[1], a0[2], a0[3], q0_[0], q0_[1], q0_[2], q0_[3], sg ? zm7[2 * kap] : z09[2 * kap], sg ? zm7[2 * kap + 1] : z09[2 * kap + 1]);
            mma(a1[0], a1[1], a1[2], a1[3], q1_[0], q1_[1], q1_[2], q1_[3], sg ? z07[2 * kap] : zm9[2 * kap], sg ? z07[2 * kap + 1] : zm9[2 * kap + 1]);
          }
        }
    SPLIT();
#pragma unroll
    for (int i = 0; i < 8; i++) {
      uint32_t h[4];
      ldsm4(h, qa + 128 * i);
      const float ci[4] = {a[i >> 1][0][2 * (i & 1)], a[i >> 1][0][2 * (i & 1) + 1], a[i >> 1][1][2 * (i & 1)], a[i >> 1][1][2 * (i & 1) + 1]};
      mmac(acc[8 + i], h[0], h[1], h[2], h[3], lb0, lb1, ci);
    }
  }
  TS(44);
  {
    uint2 a5[10], a3[10];
    const uint32_t aa = tb + T_5 + 4 * (8 + 2 * g - 2 * c);
#pragma unroll
    for (int m = 0; m < 10; m++) { a5[m] = lds64(aa + 32 * m); a3[m] = lds64(aa + 384 + 32 * m); }
    uint32_t x5[12][2], x3[12][2];
    auto ygen = [&](int kap) {
#pragma unroll
      for (int hh = 0; hh < 2; hh++) {
        float y0, y1, y2, y3;
        mma0(y0, y1, y2, y3, by[0], by[1], by[2], by[3], lds32(y0a + 128 * kap + 64 * hh), lds32(y1a + 128 * kap + 64 * hh));
        x5[kap][hh] = pack_bf(y0, y1);
        x3[kap][hh] = pack_bf(y2, y3);
      }
    };
    ygen(11); ygen(10); ygen(9); ygen(8);
#pragma unroll
    for (int kap = 11; kap >= 0; kap--) {
      if (kap >= 4) ygen(kap - 4);
#pragma unroll
      for (int sg = 0; sg < 2; sg++)
#pragma unroll
        for (int i = 4; i >= 0; i--) {
          const int be = kap + 4 + i;
          if (be <= 15) {
            const uint2 &hi = sg ? a3[2 * i + 1] : a5[2 * i + 1], &lo = sg ? a3[2 * i] : a5[2 * i];
            const uint32_t b0 = sg ? x3[kap][0] : x5[kap][0], b1 = sg ? x3[kap][1] : x5[kap][1];
            if (be < 8 && i == 0 && sg == 0) mma0(acc[be][0], acc[be][1], acc[be][2], acc[be][3], hi.x, hi.y, lo.x, lo.y, b0, b1);
            else mma(acc[be][0], acc[be][1], acc[be][2], acc[be][3], hi.x, hi.y, lo.x, lo.y, b0, b1);
          }
        }
    }
  }
  TS(45);
  {
    const uint32_t st = tb + T_ST + lane * 8;
#pragma unroll
    for (int be = 4; be < 12; be++) sts64(st + 256 * be, pack_bf(acc[be][0], acc[be][1]), pack_bf(acc[be][2], acc[be][3]));
    SPLIT();
    uint32_t F[66], qd[8][4];
    const uint32_t fa = tb + T_D + 32 + 4 * x;
#pragma unroll
    for (int i = 0; i < 32; i++) {
      const int s = 120 - (i >> 2) - 8 * (i & 3);
      uint32_t(&q)[4] = qd[i & 7];
      ldsm4(q, qa + 16 * s);
      const int m = 16 * (i & 3) + 2 * (i >> 2);
      F[m] = lds32(fa + 32 * m); F[m + 1] = lds32(fa + 32 * m + 32);
#pragma unroll
      for (int be = 15; be >= 12; be--) {
        const int de = 8 * be - s;
        float(&a)[4] = (be >= 14 && !(i & 1)) ? acc[be - 4] : acc[be];
        if (de >= 0 && be >= 14 && i == 2 * (15 - be)) mma0(a[0], a[1], a[2], a[3], q[0], q[1], q[2], q[3], F[2 * de + 1], F[2 * de]);
        else if (de >= 0) mma(a[0], a[1], a[2], a[3], q[0], q[1], q[2], q[3], F[2 * de + 1], F[2 * de]);
      }
    }
#pragma unroll
    for (int i = 0; i < 8; i++) acc[14 + (i >> 2)][i & 3] += acc[10 + (i >> 2)][i & 3];
    F[64] = lds32(fa + 32 * 64); F[65] = lds32(fa + 32 * 65);
#pragma unroll
    for (int i = 0; i < 6; i++) ldsm4(qd[i], qa + 128 * 11 - 16 * i);
    uint2 sv = lds64(st + 256 * 11);
    float ci[4] = {bf_lo(sv.x), bf_hi(sv.x), bf_lo(sv.y), bf_hi(sv.y)};
    float T[5][4];
#pragma unroll
    for (int i = 0; i < 16; i++) T[i >> 2][i & 3] = acc[12 + (i >> 2)][i & 3];
    nb_sync(NB_YZ, 160);
    TS(46);
    uint32_t held[2];
#pragma unroll
    for (int be = 11; be >= 0; be--) {
      if (be & 1) SPLITN(be);
      const uint32_t qp = qa + 128 * be;
#pragma unroll
      for (int k = 4; k >= 1; k--) mmac(T[k], qd[0][0], qd[0][1], qd[0][2], qd[0][3], F[16 * k + 1], F[16 * k], T[k - 1]);
      if (be >= 4) mmac(T[0], qd[0][0], qd[0][1], qd[0][2], qd[0][3], F[1], F[0], ci);
      else mma0(T[0][0], T[0][1], T[0][2], T[0][3], qd[0][0], qd[0][1], qd[0][2], qd[0][3], F[1], F[0]);
      ldsm4(qd[6], qp - 16 * 6);
      ldsm4(qd[7], qp - 16 * 7);
      if (be > 4) sv = lds64(st + 256 * (be - 1));
#pragma unroll
      for (int i = 1; i < 8; i++) {
#pragma unroll
        for (int k = 3; k >= 0; k--)
          mma(T[k][0], T[k][1], T[k][2], T[k][3], qd[i][0], qd[i][1], qd[i][2], qd[i][3], F[16 * k + 2 * i + 1], F[16 * k + 2 * i]);
        if (i < 7 && be > 0) ldsm4(qd[i - 1], qp - 128 - 16 * (i - 1));
        if (i == 2) {
          const uint32_t w0 = pack_bf(T[4][0], T[4][1]), w1 = pack_bf(T[4][2], T[4][3]);
          if (be & 1) { held[0] = w0; held[1] = w1; }
          else st_x(ydst + (be + 4) * 16, nz(w0), w1, held[0], held[1]);
          if ((be & 3) == 3 && be < 11) nb_arrive(NB_Y + 2 + (be >> 2), 160);
        }
        if (i == 4 && be > 4) { ci[0] = bf_lo(sv.x); ci[1] = bf_hi(sv.x); ci[2] = bf_lo(sv.y); ci[3] = bf_hi(sv.y); }
      }
    }
    nb_arrive(NB_Y + 1, 160);
#pragma unroll
    for (int B = 1; B >= 0; B--)
      st_x(ydst + B * 32, nz(pack_bf(T[2 * B][0], T[2 * B][1])), pack_bf(T[2 * B][2], T[2 * B][3]),
           pack_bf(T[2 * B + 1][0], T[2 * B + 1][1]), pack_bf(T[2 * B + 1][2], T[2 * B + 1][3]));
  }
}

__device__ __forceinline__ void dual_exp(const uint32_t* w, uint32_t* e) {
  const float L = 1.44268798828125f;
  uint32_t mx = bmax2(bmax2(w[0], w[1]), bmax2(w[2], w[3]));
  uint32_t mn = bmin2(bmin2(w[0], w[1]), bmin2(w[2], w[3]));
  mx = bmax2(mx, __shfl_xor_sync(0xffffffffu, mx, 1));
  mn = bmin2(mn, __shfl_xor_sync(0xffffffffu, mn, 1));
  mx = bmax2(mx, __shfl_xor_sync(0xffffffffu, mx, 2));
  mn = bmin2(mn, __shfl_xor_sync(0xffffffffu, mn, 2));
  const float mx0 = bf_lo(mx) * -L, mx1 = bf_hi(mx) * -L, mn0 = bf_lo(mn) * L, mn1 = bf_hi(mn) * L;
#pragma unroll
  for (int i = 0; i < 2; i++) {
    const float a0 = bf_lo(w[2 * i]), a1 = bf_hi(w[2 * i]), b0 = bf_lo(w[2 * i + 1]), b1 = bf_hi(w[2 * i + 1]);
    e[2 * i] = pack_bf(ex2(fmaf(a0, L, mx0)), ex2(fmaf(b0, L, mx0)));
    e[2 * i + 1] = pack_bf(ex2(fmaf(a1, L, mx1)), ex2(fmaf(b1, L, mx1)));
    e[4 + 2 * i] = pack_bf(ex2(fmaf(a0, -L, mn0)), ex2(fmaf(b0, -L, mn0)));
    e[5 + 2 * i] = pack_bf(ex2(fmaf(a1, -L, mn1)), ex2(fmaf(b1, -L, mn1)));
  }
}
__device__ __forceinline__ void normalise(uint32_t* e, const float (&s)[4]) {
  const uint32_t r = pack_bf(rcp(s[0]), rcp(s[2]));
  const __nv_bfloat162 rr = *(const __nv_bfloat162*)&r;
#pragma unroll
  for (int i = 0; i < 4; i++) {
    const __nv_bfloat162 v = __hmul2(*(const __nv_bfloat162*)&e[i], (i & 1) ? __high2bfloat162(rr) : __low2bfloat162(rr));
    e[i] = *(const uint32_t*)&v;
  }
}
__host__ __device__ constexpr uint64_t qdesc(uint32_t addr) { return mkdesc(addr, 128, 256, 0); }

__global__ void __launch_bounds__(NTHREADS, 1)
fused_kernel(const Params P, const __grid_constant__ CUtensorMap mx, const __grid_constant__ CUtensorMap mw,
             const __grid_constant__ CUtensorMap mo, const __grid_constant__ CUtensorMap mu,
             const __grid_constant__ CUtensorMap mout) {
  constexpr uint32_t sb = SB;
  const int tid = threadIdx.x, lane = tid & 31;
  const int warp = __shfl_sync(0xffffffffu, tid >> 5, 0);
  const int b = blockIdx.x, oct = b >> 3, i8 = b & 7;
  const int rt = (((oct & 4) ? ~oct : oct) & 3) * 2 + (i8 >> 2);
  const int hp = (oct >> 2) * 4 + (i8 & 3);

  const int wg = warp >> 2, w = warp & 3;
  const int d = b * 4 + ((tid >> 5) & 3);
  const KgenRaw raw = kgen_load(P, d, (tid >> 7) & 1, lane);
  const unsigned short dsk = __ldg((const unsigned short*)P.Dskip + d);
  const uint32_t tb = sb + OFF_T + w * T_CH;
  if (warp >= 12) {
    asm volatile("setmaxnreg.dec.sync.aligned.u32 32;");
    if (warp == 12) {
      if (lane == 0) {
#pragma unroll
        for (int i = 0; i < 9; i++) mbar_init(BAR(i), 1);
        asm volatile("fence.mbarrier_init.release.cluster;" ::: "memory");
      }
      __syncwarp();
      if (lane < 9) mbar_expect(BAR(0) + 8 * lane, lane == 0 ? 16384 : 28672);
      __syncwarp();
      nb_arrive(NB_PROD, 512);
#pragma unroll 1
      for (int kb = 0; kb < 8; kb++) {
        if (kb == U_AT) e_tma4d(sb + OFF_STG0, &mu, BAR(MB_URAW), i8 * 64, oct * 2);
        e_tma3d(sb + OFF_W + kb * 12288, &mw, BAR(MB_FULL) + 8 * kb, hp * 32, kb * 64, 0);
        if (kb < 5) e_tma2d(sb + OFF_X + (kb < 2 ? kb + 3 : kb - 2) * 16384, &mx, BAR(MB_FULL) + 8 * kb, kb * 64, rt * 256);
      }
      if (smem_u32(smem_raw) != SB) __trap();
      if (lane == 0) TS1(54);
      nb_sync(NB_GATE + 1, 64);
      if (X2_AT < 0) e_prefetch(P.x + (size_t)(rt * 256 + 128 + hp * 8) * 512, 8192);
      uint32_t slot = sb + OFF_X + 3 * 16384;
#pragma unroll 1
      for (int n = 0; n < 11; n++) {
        mbar_spin(BAR(MB_EMPTY) + 8 * n);
        const int m = n + 5;
        e_tma2d(slot, &mx, BAR(MB_FULL) + 8 * m, (m & 7) * 64, rt * 256 + (m >> 3) * 128);
        slot = slot == sb + OFF_X + 4 * 16384 ? sb + OFF_X : slot + 16384;
        if (n == X2_AT) e_prefetch(P.x + (size_t)(rt * 256 + 128 + hp * 8) * 512, 8192);
        if (n == 7) {
          e_prefetch(P.wo + (size_t)b * 2048, 4096);
          asm volatile("prefetch.tensormap [%0];" ::"l"(&mo) : "memory");
          asm volatile("prefetch.tensormap [%0];" ::"l"(&mout) : "memory");
        }
      }
#pragma unroll 1
      for (int i = 0; i < 8; i++) {
        mbar_wait(BAR(MB_EMPTY + 10) + 8 * ((0x54332222u >> (4 * i)) & 7));
        const int w0 = (0x54736210u >> (4 * i)) & 7;
        e_tma3d(sb + OFF_W + w0 * 16384, &mo, BAR(MB_WO), 0, w0 * 64, (hp & 3) * 2);
      }
    } else {
      if (warp == 13) {
        if (lane == 0) {
#pragma unroll
          for (int i = 9; i < 40; i++) mbar_init(BAR(i), i < MB_EMPTY ? 1 : 4);
          asm volatile("fence.mbarrier_init.release.cluster;" ::: "memory");
        }
        __syncwarp();
        if (lane < 14 && lane != 9) mbar_expect(BAR(MB_FULL + 8) + 8 * lane, lane == 8 ? 131072 : (lane == 10 ? 8192 : (lane == 13 ? 24576 : 16384)));
        nb_arrive(NB_GATE + 1, 64);
      } else if (warp == 14) {
        asm volatile("prefetch.tensormap [%0];" ::"l"(&mw) : "memory");
        asm volatile("prefetch.tensormap [%0];" ::"l"(&mx) : "memory");
        asm volatile("prefetch.tensormap [%0];" ::"l"(&mu) : "memory");
        e_prefetch(P.x + (size_t)(rt * 256 + hp * 8) * 512, 8192);
      }
      nb_sync(NB_PROD, 512);
      if (warp == 15) {
        const uint4 v0 = __ldg((const uint4*)P.wphi + hp * 64 + lane), v1 = __ldg((const uint4*)P.wphi + hp * 64 + 32 + lane);
        sts128(sb + OFF_PHI + (lane & 1) * 256 + (lane >> 1) * 16, v0.x, v0.y, v0.z, v0.w);
        sts128(sb + OFF_PHI + 512 + (lane & 1) * 256 + (lane >> 1) * 16, v1.x, v1.y, v1.z, v1.w);
        const uint32_t one = (((lane >> 3) ^ (lane >> 4)) & 1) ? 0u : ((lane & 1) ? 0x3F800000u : 0x3F80u);
        const int q = (lane >> 1) & 3;
        sts128(sb + OFF_EYE + lane * 16, q == 0 ? one : 0u, q == 1 ? one : 0u, q == 2 ? one : 0u, q == 3 ? one : 0u);
        sts64(sb + OFF_ONE + lane * 8, 0x3F803F80u, 0x3F803F80u);
        asm volatile("fence.proxy.async.shared::cta;" ::: "memory");
        nb_arrive(NB_KREAD, 160);
      }
      uint32_t* cnt = (uint32_t*)(P.xs + X_CNT) + (warp == 13 ? i8 : (warp == 14 ? 8 + rt : 16 + oct)) * 32;
      const unsigned target = (ld_x32(cnt) & ~15u) + 16;
      if (warp != 14) {
        if (warp == 15) mbar_wait(BAR(MB_EMPTY + ZERO_STEP));
        uint4* pz = P.xs + (warp == 13 ? X_PART + (hp * 8 + rt) * 144 : X_Y + b * 1024) + lane;
#pragma unroll 1
        for (int i = (warp == 13 ? 144 : 1024) - lane; i > 0; i -= 32, pz += 32) st_x(pz, 0, 0, 0, 0);
      }
      if (warp == 15) __syncwarp();
      else nb_sync(warp == 13 ? NB_INIT : NB_ODONE, warp == 13 ? 160 : 288);
      if (lane == 0) asm volatile("red.release.gpu.global.add.u32 [%0], %1;" ::"l"(cnt), "r"(warp == 15 ? 2 : 1) : "memory");
      if (lane == 0) TS1(warp == 13 ? 50 : (warp == 14 ? 57 : 53));
      __syncwarp();
      if (warp == 14) nb_arrive(NB_GATE + 1, 160);
      asm volatile("fence.proxy.async.shared::cta;" ::: "memory");
      if (warp == 13) cnt += ((lane & 1 ? b >> 4 : i8 ^ (lane & 4)) - i8) * 32;
#pragma unroll 1
      for (int i = 0; i < SPIN_MAX; i++) {
        unsigned v;
        asm volatile("ld.acquire.gpu.global.u32 %0, [%1];" : "=r"(v) : "l"(cnt) : "memory");
        if (__all_sync(0xffffffffu, (int)(v - target) >= 0)) break;
      }
      if (lane == 0) TS1(warp == 13 ? 51 : (warp == 14 ? 58 : 55));
      if (warp == 15) { nb_arrive(NB_YZ, 160); return; }
      asm volatile("fence.proxy.async.global;" ::: "memory");
      if (warp == 13) {
        mbar_wait(BAR(MB_EMPTY + 11));
        e_expect(BAR(MB_UFULL), 4 * U_CH);
        e_bulk(sb + OFF_U, P.xs + X_UT + b * (U_CH / 4), 4 * U_CH, BAR(MB_UFULL));
      } else {
        const uint4* src = P.xs + X_O + (rt * 4 + (hp >> 2)) * 4096;
        e_bulk(sb + OFF_X + 32768 + 57344, src + 3584, 8192, BAR(MB_O));
        e_bulk(sb + OFF_X + 32768, src, 16384, BAR(MB_O + 1));
        e_bulk(sb + OFF_X + 49152, src + 1024, 16384, BAR(MB_O + 2));
        e_bulk(sb + OFF_STG0, src + 3200, 6144, BAR(MB_O + 3));
        nb_sync(NB_BDONE, 288);
        asm volatile("fence.proxy.async.shared::cta;" ::: "memory");
        e_bulk(sb + OFF_U, src + 2048, 18432, BAR(MB_O + 3));
      }
    }
    return;
  }

  asm volatile("setmaxnreg.inc.sync.aligned.u32 160;");
  const int t = tid & 127;
  const int g = lane >> 2, c = lane & 3;
  const uint32_t kp = ((tb + 127) & ~127u) + (wg & 1) * 2048;
  const KgenAddr kad = kgen_addr(lane, kp);
  nb_sync(NB_PROD, 512);
  float k[5][4], k2048, ksc;
  if (wg) {
    kgen_unit(raw, kad, blockIdx.y, k, k2048, ksc);
    TS(40 + wg);
    if ((fu(k[0][0]) & fu(k[1][0]) & fu(k[2][0]) & fu(k[3][0]) & fu(k[4][0])) == 0xffffffffu) sts32(kp, 0);
    nb_arrive(0, 384);
    if (wg == 1) {
      uint32_t h[10];
#pragma unroll
      for (int j = 0; j < 10; j++) h[j] = hu(__floats2half2_rn(k[j >> 1][2 * (j & 1)], k[j >> 1][2 * (j & 1) + 1]));
      sts128(kp + lane * 16, h[0], h[1], h[2], h[3]);
      sts128(kp + 512 + lane * 16, h[4], h[5], h[6], h[7]);
      sts128(kp + 1024 + lane * 16, h[8], h[9], fu(k2048), fu(ksc));
      nb_arrive(NB_PREP, 256);
    }
  } else {
    nb_sync(NB_KREAD, 160);
    nb_sync(0, 384);
  }
  if (wg == 1) {
    mbar_wait(BAR(MB_URAW));
    TS(48);
    uint4* dst = P.xs + X_UT + (i8 * 64 + g) * (U_CH / 16) + (w & 1) * (U_ODD / 16) + U_PAD / 16 + oct * 8 + (w >> 1) * 4 + c;
    const int ln = ((lane >> 1) & 3) + 4 * (lane & 1);
    uint32_t r[8][4];
#pragma unroll
    for (int i = 0; i < 8; i++) ldsm4t(r[i], sb + OFF_STG0 + w * 4096 + ((lane >> 3) * 8 + ln) * 128 + ((i ^ ln) << 4));
#pragma unroll
    for (int i = 0; i < 8; i++) dst[i * (U_CH / 2)] = make_uint4(r[i][0], r[i][1], r[i][2], r[i][3]);
    nb_arrive(NB_INIT, 160);
    if (lane == 0) mbar_arrive(BAR(MB_AUX));
  }
  {
    if (wg == 2) {
#pragma unroll
      for (int j = 0; j < 5; j++) { k[j][0] *= ksc; k[j][1] *= ksc; k[j][2] *= ksc; k[j][3] *= ksc; }
      nb_sync(NB_PREP, 256);
      {
        const uint32_t src = kp + 2048 + lane * 16;
        const uint4 v0 = lds128(src), v1 = lds128(src + 512), v2 = lds128(src + 1024);
        const uint32_t h[10] = {v0.x, v0.y, v0.z, v0.w, v1.x, v1.y, v1.z, v1.w, v2.x, v2.y};
#pragma unroll
        for (int j = 0; j < 10; j++) {
          const float2 f = __half22float2(*(const __half2*)&h[j]);
          k[j >> 1][2 * (j & 1)] = fmaf(f.x, uf(v2.w), k[j >> 1][2 * (j & 1)]);
          k[j >> 1][2 * (j & 1) + 1] = fmaf(f.y, uf(v2.w), k[j >> 1][2 * (j & 1) + 1]);
        }
        k2048 += uf(v2.z);
      }
#pragma unroll
      for (int o2 = 16; o2; o2 >>= 1) k2048 += __shfl_xor_sync(0xffffffffu, k2048, o2);
      if (lane == 0) k[0][0] += bf_lo(dsk);
      __syncwarp();
      TS(34);
      build_tables(tb, lane, k, k2048);
      TS(35);
      uint4* const g_y = P.xs + X_Y;
      conv_channel(sb + OFF_U + w * U_CH, tb, lane, g_y + (size_t)d * 256 + lane);
      nb_arrive(NB_BDONE, 288);
      nb_arrive(NB_Y, 160);
      TS(37);
      if (w == 0) TSDUMP(32);
      return;
    }
    if (wg == 1) {
      mbar_wait(BAR(MB_EMPTY + 4));
      mbar_spin(BAR(MB_EMPTY + 6));
    }
    TS(wg * 16 + 1);
  }

  float acc[2][48];
  {
    uint32_t fb = BAR(MB_FULL) + 64 * wg;
    uint32_t da = (uint32_t)mkdesc(sb + OFF_X, 16, 0, 0) + (wg ? 1024 : 3072), db = (uint32_t)mkdesc(sb + OFF_W, 4096, 0, 0);
    constexpr uint64_t ha = mkdesc(0, 0, 1024, 1), hb = mkdesc(0, 0, 512, 2);
    mbar_spin(fb);
    TS(wg * 16 + 2);
#pragma unroll 1
    for (int kb = 0; kb < 8; kb++) {
      WG_FENCE();
#pragma unroll
      for (int k = 0; k < 4; k++) {
        wgmma_ss_n96(acc[0], ha | (da + 2 * k), hb | (db + 64 * k), k ? 1 : kb);
        wgmma_ss_n96(acc[1], ha | (da + 2 * k + 512), hb | (db + 64 * k), k ? 1 : kb);
      }
      WG_COMMIT();
      if (kb < 7) mbar_spin(fb + 8);
      WG_WAIT(1);
      if (kb > 0) e_arrive(fb + 8 * (MB_EMPTY - MB_FULL - 1));
      fb += 8; db += 768;
      da = da == (uint32_t)mkdesc(sb + OFF_X + 65536, 16, 0, 0) ? da - 4096 : da + 1024;
    }
    WG_WAIT(0);
    e_arrive(fb + 8 * (MB_EMPTY - MB_FULL - 1));
    SPLIT();
  }
  TS(wg * 16 + 3);

  constexpr uint32_t stg0 = sb + OFF_STG0, stg1 = sb + OFF_X + 32768;
  uint4* const g_part = P.xs + X_PART;
  uint4* const g_o = P.xs + X_O;
  constexpr uint32_t kvs = stg0;
  auto pack8 = [](const float* a) { return make_uint4(pack_bf(a[0], a[1]), pack_bf(a[2], a[3]), pack_bf(a[4], a[5]), pack_bf(a[6], a[7])); };
  auto feat = [&](const uint4 (&af)[4], float (&p)[4][8]) {
    WG_FENCE();
#pragma unroll
    for (int u = 0; u < 4; u++) wgmma_rs_n16(p[u], af[u], qdesc(sb + OFF_PHI + (u & 1) * 512), 0);
    WG_COMMIT();
  };
  auto packp = [](const float (&p)[4][8], uint32_t (&pw)[16]) {
#pragma unroll
    for (int i = 0; i < 16; i++) pw[i] = pack_bf(p[i >> 2][(i & 1) + 2 * (i & 2)], p[i >> 2][(i & 1) + 2 * (i & 2) + 2]);
  };
  auto contract = [&](float (&kc)[20], uint32_t stg, int acc_in) {
    WG_FENCE();
#pragma unroll
    for (int s = 0; s < 8; s++) wgmma_ss_n40(kc, qdesc(stg + s * SLAB), qdesc(stg + s * SLAB + 2048), s ? 1 : acc_in);
    WG_COMMIT();
    WG_WAIT(0);
  };
  uint32_t eq[32];
  {
    uint4 af[4], aq[4], vp[4];
    float p[4][8];
#pragma unroll
    for (int u = 0; u < 4; u++) af[u] = pack8(acc[u >> 1] + 16 + 8 * (u & 1));
    feat(af, p);
#pragma unroll
    for (int u = 0; u < 4; u++) { aq[u] = pack8(acc[u >> 1] + 8 * (u & 1)); vp[u] = pack8(acc[u >> 1] + 32 + 8 * (u & 1)); }
    WG_WAIT(0);
    uint32_t pw[16], ek[32];
    packp(p, pw);
#pragma unroll
    for (int u = 0; u < 4; u++) dual_exp(pw + 4 * u, ek + 8 * u);
    TS(wg * 16 + 12);
    mbar_spin(wg ? BAR(MB_EMPTY + 15) : BAR(MB_AUX));
    float rs[8][4];
    WG_FENCE();
#pragma unroll
    for (int i = 0; i < 8; i++) wgmma_rs_n8(rs[i], make_uint4(ek[4 * i], ek[4 * i + 1], ek[4 * i + 2], ek[4 * i + 3]), qdesc(sb + OFF_ONE), 0);
    WG_COMMIT();
    feat(aq, p);
    const uint32_t sl = (wg ? stg1 : stg0) + w * SLAB + lane * 16;
#pragma unroll
    for (int i = 0; i < 4; i++) stsm4(sl + (i >> 1) * 4 * SLAB + 2048 + (i & 1) * 512, vp[i].x, vp[i].y, vp[i].z, vp[i].w);
    sts128(sl + (lane >> 4) * (4 * SLAB - 256) + 3072, 0x3F803F80u, 0x3F803F80u, 0x3F803F80u, 0x3F803F80u);
    WG_WAIT(1);
#pragma unroll
    for (int i = 0; i < 8; i++) {
      normalise(ek + 4 * i, rs[i]);
      stsm4(sl + (i >> 2) * 4 * SLAB + (i & 3) * 512, ek[4 * i], ek[4 * i + 1], ek[4 * i + 2], ek[4 * i + 3]);
    }
    asm volatile("fence.proxy.async.shared::cta;" ::: "memory");
    TS(wg * 16 + 13);
    if (wg) {
      nb_arrive(NB_ST0, 256);
      nb_arrive(NB_GATE, 256);
    } else {
      float kc[20];
      uint4* pp = g_part + (size_t)(hp * 8 + rt) * 144 + t;
      uint32_t* pz = (uint32_t*)(pp - t + 128) + w * 16 + c * 8 + g;
      asm volatile("" : "+l"(pp), "+l"(pz));
      nb_sync(NB_WG0, 128);
      contract(kc, stg0, 0);
      mbar_wait(BAR(MB_UFULL));
      TS(15);
      nb_sync(NB_ST0, 256);
      contract(kc, stg1, 1);
      TS(6);
      float kv[8];
#pragma unroll
      for (int i = 0; i < 8; i++) kv[i] = w & 2 ? kc[8 + i] : kc[i];
      st_x(pp, nz(pack_bf(kv[0], kv[1])), pack_bf(kv[2], kv[3]), pack_bf(kv[4], kv[5]), pack_bf(kv[6], kv[7]));
      if (c < 2) st_x32(pz, nz(fu(c ? kc[18] : kc[16])));
      TS(5);
    }
    SPLIT();
    WG_WAIT(0);
    packp(p, pw);
#pragma unroll
    for (int u = 0; u < 4; u++) dual_exp(pw + 4 * u, eq + 8 * u);
    SPLIT();
  }
  TS(wg * 16 + 4);
  if (wg == 1) {
    mbar_wait(BAR(MB_UFULL));
    const uint4* ps = g_part + (size_t)hp * 8 * 144 + t;
    const uint32_t* zs = (const uint32_t*)(g_part + (size_t)(hp * 8 + (lane >> 4) * 4) * 144 + 128) + w * 16 + (lane & 15);
    uint4 v[8];
    uint32_t zv[4];
#pragma unroll 1
    for (int it = 0; it < SPIN_MAX; it++) {
#pragma unroll
      for (int i = 0; i < 8; i++) v[i] = ld_x(ps + i * 144);
#pragma unroll
      for (int i = 0; i < 4; i++) zv[i] = ld_x32(zs + i * 576);
      uint32_t m = min(min(zv[0], zv[1]), min(zv[2], zv[3]));
#pragma unroll
      for (int i = 0; i < 8; i++) m = min(m, v[i].x);
      if (__all_sync(0xffffffffu, m != 0)) break;
    }
    float s[8];
    WG_FENCE();
#pragma unroll
    for (int r = 0; r < 8; r++) wgmma_rs_n16(s, v[r], qdesc(sb + OFF_EYE), r);
    WG_COMMIT();
    float zsum = (uf(zv[0]) + uf(zv[1])) + (uf(zv[2]) + uf(zv[3]));
    zsum += __shfl_xor_sync(0xffffffffu, zsum, 16);
    const uint32_t z1 = pack_bf(zsum, 1.f);
    if (lane < 16) sts128(kvs + w * 768 + 512 + lane * 16, z1, z1, z1, z1);
    WG_WAIT(0);
    stsm4(kvs + w * 768 + lane * 16, pack_bf(s[0], s[1]), pack_bf(s[2], s[3]), pack_bf(s[4], s[5]), pack_bf(s[6], s[7]));
    asm volatile("fence.proxy.async.shared::cta;" ::: "memory");
    TS(22);
  }
  nb_sync(NB_KV, 256);
  {
    float n[8][12];
    WG_FENCE();
#pragma unroll
    for (int i = 0; i < 8; i++) wgmma_rs_n24(n[i], make_uint4(eq[4 * i], eq[4 * i + 1], eq[4 * i + 2], eq[4 * i + 3]), qdesc(kvs + (i & 3) * 768), 0);
    WG_COMMIT();
    uint32_t* od = (uint32_t*)(g_o + (size_t)((rt * 4 + wg * 2) * 32 + hp * 2) * 128) + w * 64 + lane;
    WG_WAIT(0);
#pragma unroll
    for (int u = 0; u < 4; u++) {
      float(&np)[12] = n[2 * u];
      const float(&nm)[12] = n[2 * u + 1];
      const float q0 = np[9] * rcp(nm[9]), q1 = np[11] * rcp(nm[11]);
      const float r0 = rcp(fmaf(nm[8], q0, fmaf(np[9], 1e-6f, np[8]))), r1 = rcp(fmaf(nm[10], q1, fmaf(np[11], 1e-6f, np[10])));
#pragma unroll
      for (int i = 0; i < 8; i++) np[i] = fmaf(nm[i], (i & 2) ? q1 : q0, np[i]);
      uint32_t* o = od + (u >> 1) * 16384 + (u & 1) * 512;
      o[0] = pack_bf(np[0] * r0, np[1] * r0);
      o[32] = pack_bf(np[2] * r1, np[3] * r1);
      o[256] = pack_bf(np[4] * r0, np[5] * r0);
      o[288] = pack_bf(np[6] * r1, np[7] * r1);
      if (u == 1) SPLIT();
    }
  }
  TS(wg * 16 + 7);
  nb_arrive(NB_ODONE, 288);
  if (wg) {
    const uint4* src = P.xs + X_Y + (oct * 32 + c * 8) * 256 + (2 * w + (g >> 2)) * 32 + i8 * 4 + (g & 3);
    __nv_bfloat16* dst = P.out + (size_t)((2 * w + (g >> 2)) * 256 + i8 * 16 + (g & 3) * 2) * 1024 + 512 + oct * 32 + c * 8;
    nb_sync(NB_GATE + 1, 160);
    nb_sync(NB_Y + w, 160);
    uint4 v[8];
#pragma unroll 1
    for (int it = 0; it < SPIN_MAX; it++) {
      uint32_t m = 0xffffffffu;
#pragma unroll
      for (int i = 0; i < 8; i++) v[i] = ld_x(src + i * 256);
#pragma unroll
      for (int i = 0; i < 8; i++) m = min(m, v[i].x);
      if (__all_sync(0xffffffffu, m != 0)) break;
    }
#pragma unroll
    for (int i = 0; i < 8; i++) *(uint4*)(dst + (size_t)((i >> 2) * 128 + ((i >> 1) & 1) * 8 + (i & 1)) * 1024) = tr_row(v, i);
    TS(31);
    GT(63);
    if (w == 0) TSDUMP(16);
    return;
  }
  mbar_wait(BAR(MB_WO));
  nb_sync(NB_BDONE, 288);
  TS(8);
  mbar_spin(BAR(MB_O));
  TS(9);
  constexpr uint64_t ha = mkdesc(0, 0, 128, 0), hb = mkdesc(0, 0, 1024, 1);
  constexpr uint32_t da0 = (uint32_t)mkdesc(stg1, 1024, 0, 0), db0 = (uint32_t)mkdesc(sb + OFF_W, 8192, 0, 0);
  const uint32_t ot = ((sb + OFF_T + 1023) & ~1023u) + w * 4096;
  auto store_half = [&](const float* oc, int hf) {
#pragma unroll
    for (int i = 0; i < 8; i += 2)
      stsm4(ot + hf * 2048 + (lane & 15) * 128 + (((i + (lane >> 4)) ^ lane) & 7) * 16, pack_bf(oc[4 * i], oc[4 * i + 1]),
            pack_bf(oc[4 * i + 2], oc[4 * i + 3]), pack_bf(oc[4 * i + 4], oc[4 * i + 5]), pack_bf(oc[4 * i + 6], oc[4 * i + 7]));
    asm volatile("fence.proxy.async.shared::cta;" ::: "memory");
    __syncwarp();
    e_store2d(&mout, ot + hf * 2048, (hp & 3) * 128 + hf * 64, (rt * 4 + (hp >> 2)) * 64 + w * 16);
  };
  float oc[64];
#pragma unroll 1
  for (int j = 0; j < 8; j++) {
    const int kb = (j + 7) & 7;
    if ((j & 1) && j < 6) mbar_spin(BAR(MB_O + 1) + 4 * (j - 1));
    WG_FENCE();
#pragma unroll
    for (int k = 0; k < 4; k++) wgmma_ss_n128(oc, ha | (da0 + 512 * kb + 128 * k), hb | (db0 + 1024 * kb + 128 * k), k ? 1 : j);
    WG_COMMIT();
  }
  WG_WAIT(0);
  TS(10);
  store_half(oc, 0);
  store_half(oc + 32, 1);
  asm volatile(ELECT "cp.async.bulk.commit_group;\n@p cp.async.bulk.wait_group.read 0;\n}\n" ::: "memory");
  TS(wg * 16 + 11);
  GT(61 + wg);
  if (w == 0) TSDUMP(0);
  if (w == 1) TSDUMP(48);
}

typedef CUresult (*EncodeFn)(CUtensorMap*, CUtensorMapDataType, cuuint32_t, void*, const cuuint64_t*, const cuuint64_t*,
                             const cuuint32_t*, const cuuint32_t*, CUtensorMapInterleave, CUtensorMapSwizzle,
                             CUtensorMapL2promotion, CUtensorMapFloatOOBfill);

}

extern "C" void kernel_launch(void* const* d_in, const int* in_sizes, int n_in, void* d_out, int out_size) {
  (void)in_sizes; (void)n_in; (void)out_size;
  void* fn = nullptr;
  cudaDriverEntryPointQueryResult qr;
  cudaGetDriverEntryPoint("cuTensorMapEncodeTiled", &fn, cudaEnableDefault, &qr);
  EncodeFn enc = (EncodeFn)fn;
  CUtensorMap mx, mw, mo, mu, mout;
  const cuuint32_t es[5] = {1, 1, 1, 1, 1};
  {
    cuuint64_t dims[2] = {512, 2048}, st[1] = {1024};
    cuuint32_t box[2] = {64, 128};
    enc(&mx, CU_TENSOR_MAP_DATA_TYPE_BFLOAT16, 2, d_in[0], dims, st, box, es, CU_TENSOR_MAP_INTERLEAVE_NONE,
        CU_TENSOR_MAP_SWIZZLE_128B, CU_TENSOR_MAP_L2_PROMOTION_L2_128B, CU_TENSOR_MAP_FLOAT_OOB_FILL_NONE);
  }
  {
    cuuint64_t dims[3] = {512, 512, 3}, st[2] = {3072, 1024};
    cuuint32_t box[3] = {32, 64, 3};
    enc(&mw, CU_TENSOR_MAP_DATA_TYPE_BFLOAT16, 3, d_in[1], dims, st, box, es, CU_TENSOR_MAP_INTERLEAVE_NONE,
        CU_TENSOR_MAP_SWIZZLE_64B, CU_TENSOR_MAP_L2_PROMOTION_L2_128B, CU_TENSOR_MAP_FLOAT_OOB_FILL_NONE);
  }
  {
    cuuint64_t dims[3] = {64, 512, 8}, st[2] = {1024, 128};
    cuuint32_t box[3] = {64, 64, 2};
    enc(&mo, CU_TENSOR_MAP_DATA_TYPE_BFLOAT16, 3, d_in[3], dims, st, box, es, CU_TENSOR_MAP_INTERLEAVE_NONE,
        CU_TENSOR_MAP_SWIZZLE_128B, CU_TENSOR_MAP_L2_PROMOTION_L2_128B, CU_TENSOR_MAP_FLOAT_OOB_FILL_NONE);
  }
  {
    cuuint64_t dims[4] = {512, 4, 16, 32}, st[3] = {16384, 1024, 65536};
    cuuint32_t box[4] = {64, 4, 16, 2};
    enc(&mu, CU_TENSOR_MAP_DATA_TYPE_BFLOAT16, 4, d_in[4], dims, st, box, es, CU_TENSOR_MAP_INTERLEAVE_NONE,
        CU_TENSOR_MAP_SWIZZLE_128B, CU_TENSOR_MAP_L2_PROMOTION_L2_128B, CU_TENSOR_MAP_FLOAT_OOB_FILL_NONE);
  }
  {
    cuuint64_t dims[2] = {1024, 2048}, st[1] = {2048};
    cuuint32_t box[2] = {64, 16};
    enc(&mout, CU_TENSOR_MAP_DATA_TYPE_BFLOAT16, 2, d_out, dims, st, box, es, CU_TENSOR_MAP_INTERLEAVE_NONE,
        CU_TENSOR_MAP_SWIZZLE_128B, CU_TENSOR_MAP_L2_PROMOTION_NONE, CU_TENSOR_MAP_FLOAT_OOB_FILL_NONE);
  }
  Params P;
  P.x = (const __nv_bfloat16*)d_in[0];
  P.wphi = (const __nv_bfloat16*)d_in[2];
  P.wo = (const __nv_bfloat16*)d_in[3];
  P.logA = (const __nv_bfloat16*)d_in[5];
  P.Aim = (const __nv_bfloat16*)d_in[6];
  P.Cre = (const __nv_bfloat16*)d_in[7];
  P.Cim = (const __nv_bfloat16*)d_in[8];
  P.logdt = (const __nv_bfloat16*)d_in[9];
  P.Dskip = (const __nv_bfloat16*)d_in[10];
  P.out = (__nv_bfloat16*)d_out;
  cudaGetSymbolAddress((void**)&P.xs, g_x);
  P.ts = nullptr;
  cudaFuncSetAttribute(fused_kernel, cudaFuncAttributeMaxDynamicSharedMemorySize, SMEM_BYTES);
  fused_kernel<<<NCTA, NTHREADS, SMEM_BYTES>>>(P, mx, mw, mo, mu, mout);
}
```

```cpp
#include <cuda_runtime.h>
#include <cuda_bf16.h>
#include <cuda_fp16.h>
#include <cuda.h>
#include <stdint.h>

#define DBG_TS 0

namespace {

constexpr int NTHREADS = 512;
constexpr int NCTA = 128;
constexpr int OFF_W = 0;
constexpr int OFF_X = 98304;
constexpr int OFF_U = OFF_X + 65536;
constexpr int U_CH = 4416, U_ODD = 2240, U_PAD = 128;
constexpr int OFF_STG0 = OFF_U + 18432;
constexpr int SLAB = 3328;
constexpr int OFF_T = OFF_STG0 + 8 * SLAB;
constexpr int T_CH = 5216;
constexpr int T_D = 0;
constexpr int T_5 = 2144;
constexpr int T_3 = T_5 + 384;
constexpr int T_7 = T_5 + 1024;
constexpr int T_9 = T_7 + 320;
constexpr int T_KC = T_9 + 320;
constexpr int T_ST = T_5 - 1024;
constexpr int OFF_PHI = OFF_T + 4 * T_CH;
constexpr int OFF_EYE = OFF_PHI + 1024, OFF_ONE = OFF_EYE + 512;
constexpr int OFF_BAR = OFF_ONE + 256;
constexpr int SMEM_BYTES = OFF_BAR + 512 + 256 * DBG_TS;
constexpr uint32_t SB = 1024;
static_assert(T_KC + 2 * 656 <= T_CH, "table size");
static_assert(SMEM_BYTES <= 232448, "smem");
constexpr int MB_URAW = 0, MB_FULL = 1  , MB_WO = 17, MB_UFULL = 18, MB_O = 19  ,
              MB_EMPTY = 23  , MB_AUX = 39;
__host__ __device__ constexpr uint32_t BAR(int i) { return SB + OFF_BAR + 8 * i; }
constexpr int NB_WG0 = 1, NB_ODONE = 2, NB_ST0 = 3  , NB_KV = 5, NB_YZ = 6, NB_INIT = 7, NB_PREP = 8, NB_PROD = 9, NB_KREAD = 10, NB_BDONE = 11, NB_GATE = 12,
              NB_Y = 7  ;
#define X2_AT -1
#define GATE_B 2
#define POLL 0
#define GATE_AT 1
#define WARM_K 1
#define KG_AFTER 0
#define U_AT 2
#define ZERO_STEP 12
constexpr int SPIN_MAX = 1 << 16;

constexpr int X_CNT = 0;
constexpr int X_PART = 256;
constexpr int X_O = X_PART + 16 * 8 * 144;
constexpr int X_Y = X_O + 32 * 32 * 128;
constexpr int X_UT = X_Y + 512 * 8 * 32;
constexpr int X_SIZE = X_UT + 512 * (U_CH / 16);
__device__ __align__(128) uint4 g_x[X_SIZE];
extern __shared__ uint8_t smem_raw[];
#define TS(i) do {} while (0)
#define TS1(i) do {} while (0)
#define GT(i) do {} while (0)
#define TSDUMP(base) do {} while (0)

__device__ __forceinline__ uint32_t smem_u32(const void* p) { return (uint32_t)__cvta_generic_to_shared(p); }
__device__ __forceinline__ void mbar_arrive(uint32_t b) {
  asm volatile("mbarrier.arrive.shared::cta.b64 _, [%0];" ::"r"(b) : "memory");
}
__device__ __forceinline__ void mbar_wait(uint32_t b) {
  uint32_t done = 0;
#pragma unroll 1
  for (int i = 0; i < SPIN_MAX && !done; i++) {
    asm volatile("{\n.reg .pred p;\nmbarrier.try_wait.parity.shared::cta.b64 p, [%1], 0, 4000;\nselp.u32 %0, 1, 0, p;\n}\n"
                 : "=r"(done) : "r"(b) : "memory");
  }
}
__device__ __forceinline__ void mbar_spin(uint32_t b) {
  uint32_t done = 0;
#pragma unroll 1
  for (int i = 0; i < (SPIN_MAX << 4) && !done; i++) {
    asm volatile("{\n.reg .pred p;\nmbarrier.try_wait.parity.shared::cta.b64 p, [%1], 0;\nselp.u32 %0, 1, 0, p;\n}\n"
                 : "=r"(done) : "r"(b) : "memory");
  }
}
__device__ __forceinline__ void mbar_init(uint32_t b, int n) {
  asm volatile("mbarrier.init.shared::cta.b64 [%0], %1;" ::"r"(b), "r"(n) : "memory");
}
__device__ __forceinline__ void mbar_expect(uint32_t b, int bytes) {
  asm volatile("mbarrier.arrive.expect_tx.shared::cta.b64 _, [%0], %1;" ::"r"(b), "r"(bytes) : "memory");
}
__device__ __forceinline__ void nb_sync(int id, int n) { asm volatile("bar.sync %0, %1;" ::"r"(id), "r"(n) : "memory"); }
__device__ __forceinline__ void nb_arrive(int id, int n) { asm volatile("bar.arrive %0, %1;" ::"r"(id), "r"(n) : "memory"); }
#define ELECT "{\n.reg .pred p;\nelect.sync _|p, 0xffffffff;\n@p "
__device__ __forceinline__ void e_arrive(uint32_t b) {
  asm volatile(ELECT "mbarrier.arrive.shared::cta.b64 _, [%0];\n}\n" ::"r"(b) : "memory");
}
__device__ __forceinline__ void e_expect(uint32_t b, int bytes) {
  asm volatile(ELECT "mbarrier.arrive.expect_tx.shared::cta.b64 _, [%0], %1;\n}\n" ::"r"(b), "r"(bytes) : "memory");
}
__device__ __forceinline__ void e_tma2d(uint32_t dst, const CUtensorMap* m, uint32_t bar, int c0, int c1) {
  asm volatile(ELECT "cp.async.bulk.tensor.2d.shared::cluster.global.mbarrier::complete_tx::bytes [%0], [%1, {%3,%4}], [%2];\n}\n"
               ::"r"(dst), "l"(m), "r"(bar), "r"(c0), "r"(c1) : "memory");
}
__device__ __forceinline__ void e_tma3d(uint32_t dst, const CUtensorMap* m, uint32_t bar, int c0, int c1, int c2) {
  asm volatile(ELECT "cp.async.bulk.tensor.3d.shared::cluster.global.mbarrier::complete_tx::bytes [%0], [%1, {%3,%4,%5}], [%2];\n}\n"
               ::"r"(dst), "l"(m), "r"(bar), "r"(c0), "r"(c1), "r"(c2) : "memory");
}
__device__ __forceinline__ void e_tma4d(uint32_t dst, const CUtensorMap* m, uint32_t bar, int c0, int c3) {
  asm volatile(ELECT "cp.async.bulk.tensor.4d.shared::cluster.global.mbarrier::complete_tx::bytes [%0], [%1, {%3,%5,%5,%4}], [%2];\n}\n"
               ::"r"(dst), "l"(m), "r"(bar), "r"(c0), "r"(c3), "r"(0) : "memory");
}
__device__ __forceinline__ void e_bulk(uint32_t dst, const void* src, int bytes, uint32_t bar) {
  asm volatile(ELECT "cp.async.bulk.shared::cluster.global.mbarrier::complete_tx::bytes [%0], [%1], %2, [%3];\n}\n"
               ::"r"(dst), "l"(src), "r"(bytes), "r"(bar) : "memory");
}
__device__ __forceinline__ void e_prefetch(const void* p, int bytes) {
  asm volatile(ELECT "cp.async.bulk.prefetch.L2.global [%0], %1;\n}\n" ::"l"(p), "r"(bytes) : "memory");
}
__device__ __forceinline__ void e_store2d(const CUtensorMap* m, uint32_t src, int c0, int c1) {
  asm volatile(ELECT "cp.async.bulk.tensor.2d.global.shared::cta.bulk_group [%0, {%2,%3}], [%1];\n}\n"
               ::"l"(m), "r"(src), "r"(c0), "r"(c1) : "memory");
}
__host__ __device__ constexpr uint64_t mkdesc(uint32_t addr, uint32_t lbo, uint32_t sbo, int swz) {
  return (uint64_t)((addr & 0x3FFFF) >> 4) | ((uint64_t)(lbo >> 4) << 16) | ((uint64_t)(sbo >> 4) << 32) |
         ((uint64_t)swz << 62);
}
#define SPLIT() asm volatile("{\n.reg .pred p;\nsetp.eq.u32 p, %0, %1;\n@p exit;\n}\n" ::"r"(blockIdx.y), "n"(__LINE__) : "memory")
#define SPLITN(n) asm volatile("{\n.reg .pred p;\nsetp.eq.u32 p, %0, %1;\n@p exit;\n}\n" ::"r"(blockIdx.y), "r"(4096 + (n)) : "memory")
#define WG_FENCE() asm volatile("wgmma.fence.sync.aligned;" ::: "memory")
#define WG_COMMIT() asm volatile("wgmma.commit_group.sync.aligned;" ::: "memory")
#define WG_WAIT(n) asm volatile("wgmma.wait_group.sync.aligned " #n ";" ::: "memory")

__device__ __forceinline__ void mma(float& d0, float& d1, float& d2, float& d3, uint32_t a0, uint32_t a1, uint32_t a2,
                                    uint32_t a3, uint32_t b0, uint32_t b1) {
  asm volatile("mma.sync.aligned.m16n8k16.row.col.f32.bf16.bf16.f32 {%0,%1,%2,%3},{%4,%5,%6,%7},{%8,%9},{%0,%1,%2,%3};"
               : "+f"(d0), "+f"(d1), "+f"(d2), "+f"(d3)
               : "r"(a0), "r"(a1), "r"(a2), "r"(a3), "r"(b0), "r"(b1));
}
__device__ __forceinline__ void mmac(float (&d)[4], uint32_t a0, uint32_t a1, uint32_t a2, uint32_t a3, uint32_t b0,
                                     uint32_t b1, const float (&c)[4]) {
  asm volatile("mma.sync.aligned.m16n8k16.row.col.f32.bf16.bf16.f32 {%0,%1,%2,%3},{%4,%5,%6,%7},{%8,%9},{%10,%11,%12,%13};"
               : "=f"(d[0]), "=f"(d[1]), "=f"(d[2]), "=f"(d[3])
               : "r"(a0), "r"(a1), "r"(a2), "r"(a3), "r"(b0), "r"(b1), "f"(c[0]), "f"(c[1]), "f"(c[2]), "f"(c[3]));
}
__device__ __forceinline__ void mma_p(int p, float (&d)[4], uint32_t a0, uint32_t a1, uint32_t a2, uint32_t a3, uint32_t b0, uint32_t b1) {
  asm volatile("{\n.reg .pred q;\nsetp.ne.b32 q, %10, 0;\n"
               "@q mma.sync.aligned.m16n8k16.row.col.f32.bf16.bf16.f32 {%0,%1,%2,%3},{%4,%5,%6,%7},{%8,%9},{%0,%1,%2,%3};\n}\n"
               : "+f"(d[0]), "+f"(d[1]), "+f"(d[2]), "+f"(d[3])
               : "r"(a0), "r"(a1), "r"(a2), "r"(a3), "r"(b0), "r"(b1), "r"(p));
}
__device__ __forceinline__ void mmac_p(int p, float (&d)[4], uint32_t a0, uint32_t a1, uint32_t a2, uint32_t a3, uint32_t b0,
                                       uint32_t b1, const float (&c)[4]) {
  asm volatile("{\n.reg .pred q;\nsetp.ne.b32 q, %14, 0;\n"
               "@q mma.sync.aligned.m16n8k16.row.col.f32.bf16.bf16.f32 {%0,%1,%2,%3},{%4,%5,%6,%7},{%8,%9},{%10,%11,%12,%13};\n}\n"
               : "+f"(d[0]), "+f"(d[1]), "+f"(d[2]), "+f"(d[3])
               : "r"(a0), "r"(a1), "r"(a2), "r"(a3), "r"(b0), "r"(b1), "f"(c[0]), "f"(c[1]), "f"(c[2]), "f"(c[3]), "r"(p));
}
__device__ __forceinline__ void mma_h(float (&d)[4], const uint32_t (&a)[4], uint32_t b0, uint32_t b1) {
  asm volatile("mma.sync.aligned.m16n8k16.row.col.f32.f16.f16.f32 {%0,%1,%2,%3},{%4,%5,%6,%7},{%8,%9},{%0,%1,%2,%3};"
               : "+f"(d[0]), "+f"(d[1]), "+f"(d[2]), "+f"(d[3]) : "r"(a[0]), "r"(a[1]), "r"(a[2]), "r"(a[3]), "r"(b0), "r"(b1));
}
__device__ __forceinline__ void mma0(float& d0, float& d1, float& d2, float& d3, uint32_t a0, uint32_t a1, uint32_t a2,
                                     uint32_t a3, uint32_t b0, uint32_t b1) {
  asm volatile("mma.sync.aligned.m16n8k16.row.col.f32.bf16.bf16.f32 {%0,%1,%2,%3},{%4,%5,%6,%7},{%8,%9},{%10,%10,%10,%10};"
               : "=f"(d0), "=f"(d1), "=f"(d2), "=f"(d3)
               : "r"(a0), "r"(a1), "r"(a2), "r"(a3), "r"(b0), "r"(b1), "f"(0.f));
}
__device__ __forceinline__ uint32_t pack_bf(float lo, float hi) {
  uint32_t r;
  asm("cvt.rn.bf16x2.f32 %0, %1, %2;" : "=r"(r) : "f"(hi), "f"(lo));
  return r;
}
__device__ __forceinline__ float bf_lo(uint32_t w) { return __uint_as_float(w << 16); }
__device__ __forceinline__ float bf_hi(uint32_t w) { return __uint_as_float(w & 0xffff0000u); }
__device__ __forceinline__ float bf_round(float x) { return __bfloat162float(__float2bfloat16_rn(x)); }
__device__ __forceinline__ uint32_t bmax2(uint32_t a, uint32_t b) {
  uint32_t r; asm("max.bf16x2 %0, %1, %2;" : "=r"(r) : "r"(a), "r"(b)); return r;
}
__device__ __forceinline__ uint32_t bmin2(uint32_t a, uint32_t b) {
  uint32_t r; asm("min.bf16x2 %0, %1, %2;" : "=r"(r) : "r"(a), "r"(b)); return r;
}
__device__ __forceinline__ float ex2(float x) { float r; asm("ex2.approx.ftz.f32 %0, %1;" : "=f"(r) : "f"(x)); return r; }
__device__ __forceinline__ float rcp(float x) { float r; asm("rcp.approx.ftz.f32 %0, %1;" : "=f"(r) : "f"(x)); return r; }
__device__ __forceinline__ void ldsm4(uint32_t (&r)[4], uint32_t a) {
  asm volatile("ldmatrix.sync.aligned.m8n8.x4.shared.b16 {%0,%1,%2,%3}, [%4];"
               : "=r"(r[0]), "=r"(r[1]), "=r"(r[2]), "=r"(r[3]) : "r"(a) : "memory");
}
__device__ __forceinline__ void ldsm4t(uint32_t (&r)[4], uint32_t a) {
  asm volatile("ldmatrix.sync.aligned.m8n8.x4.trans.shared.b16 {%0,%1,%2,%3}, [%4];"
               : "=r"(r[0]), "=r"(r[1]), "=r"(r[2]), "=r"(r[3]) : "r"(a) : "memory");
}
__device__ __forceinline__ void stsm4(uint32_t a, uint32_t r0, uint32_t r1, uint32_t r2, uint32_t r3) {
  asm volatile("stmatrix.sync.aligned.m8n8.x4.shared.b16 [%0], {%1,%2,%3,%4};"
               ::"r"(a), "r"(r0), "r"(r1), "r"(r2), "r"(r3) : "memory");
}
__device__ __forceinline__ uint32_t lds32(uint32_t a) {
  uint32_t r; asm volatile("ld.shared.u32 %0, [%1];" : "=r"(r) : "r"(a) : "memory"); return r;
}
__device__ __forceinline__ uint32_t lds16(uint32_t a) {
  uint32_t r; asm volatile("{\n.reg .u16 h;\nld.shared.u16 h, [%1];\ncvt.u32.u16 %0, h;\n}\n" : "=r"(r) : "r"(a) : "memory"); return r;
}
__device__ __forceinline__ uint2 lds64(uint32_t a) {
  uint2 r; asm volatile("ld.shared.v2.u32 {%0,%1}, [%2];" : "=r"(r.x), "=r"(r.y) : "r"(a) : "memory"); return r;
}
__device__ __forceinline__ uint4 lds128(uint32_t a) {
  uint4 r;
  asm volatile("ld.shared.v4.u32 {%0,%1,%2,%3}, [%4];" : "=r"(r.x), "=r"(r.y), "=r"(r.z), "=r"(r.w) : "r"(a) : "memory");
  return r;
}
__device__ __forceinline__ void sts32(uint32_t a, uint32_t v) { asm volatile("st.shared.u32 [%0], %1;" ::"r"(a), "r"(v) : "memory"); }
__device__ __forceinline__ void sts16(uint32_t a, uint32_t v) {
  asm volatile("{\n.reg .u16 h;\ncvt.u16.u32 h, %1;\nst.shared.u16 [%0], h;\n}\n" ::"r"(a), "r"(v) : "memory");
}
__device__ __forceinline__ void sts64(uint32_t a, uint32_t x, uint32_t y) {
  asm volatile("st.shared.v2.u32 [%0], {%1,%2};" ::"r"(a), "r"(x), "r"(y) : "memory");
}
__device__ __forceinline__ void sts128(uint32_t a, uint32_t x, uint32_t y, uint32_t z, uint32_t w) {
  asm volatile("st.shared.v4.u32 [%0], {%1,%2,%3,%4};" ::"r"(a), "r"(x), "r"(y), "r"(z), "r"(w) : "memory");
}
__device__ __forceinline__ uint4 ld_x(const uint4* p) {
  uint4 r;
  asm volatile("{\n.reg .b128 t;\nld.relaxed.gpu.global.b128 t, [%4];\nmov.b128 {%0,%1,%2,%3}, t;\n}\n"
               : "=r"(r.x), "=r"(r.y), "=r"(r.z), "=r"(r.w) : "l"(p) : "memory");
  return r;
}
__device__ __forceinline__ uint32_t ld_x32(const uint32_t* p) {
  uint32_t r; asm volatile("ld.relaxed.gpu.global.u32 %0, [%1];" : "=r"(r) : "l"(p) : "memory"); return r;
}
__device__ __forceinline__ void st_x(uint4* p, uint32_t x, uint32_t y, uint32_t z, uint32_t w) {
  asm volatile("{\n.reg .b128 t;\nmov.b128 t, {%1,%2,%3,%4};\nst.relaxed.gpu.global.b128 [%0], t;\n}\n"
               ::"l"(p), "r"(x), "r"(y), "r"(z), "r"(w) : "memory");
}
__device__ __forceinline__ void st_x_p(int p, uint4* a, uint32_t x, uint32_t y, uint32_t z, uint32_t w) {
  asm volatile("{\n.reg .b128 t;\n.reg .pred q;\nsetp.ne.b32 q, %5, 0;\nmov.b128 t, {%1,%2,%3,%4};\n@q st.relaxed.gpu.global.b128 [%0], t;\n}\n"
               ::"l"(a), "r"(x), "r"(y), "r"(z), "r"(w), "r"(p) : "memory");
}
__device__ __forceinline__ void sts64_p(int p, uint32_t a, uint32_t x, uint32_t y) {
  asm volatile("{\n.reg .pred q;\nsetp.ne.b32 q, %3, 0;\n@q st.shared.v2.u32 [%0], {%1,%2};\n}\n" ::"r"(a), "r"(x), "r"(y), "r"(p) : "memory");
}
__device__ __forceinline__ void st_x32(uint32_t* p, uint32_t x) {
  asm volatile("st.relaxed.gpu.global.u32 [%0], %1;" ::"l"(p), "r"(x) : "memory");
}
__device__ __forceinline__ uint32_t nz(uint32_t w) { return max(w, 1u); }
__device__ __forceinline__ uint32_t fu(float x) { return __float_as_uint(x); }
__device__ __forceinline__ float uf(uint32_t x) { return __uint_as_float(x); }

__device__ __forceinline__ void wgmma_ss_n96(float (&d)[48], uint64_t da, uint64_t db, int sc) {
  asm volatile("{\n.reg .pred p;\nsetp.ne.b32 p, %50, 0;\n"
      "wgmma.mma_async.sync.aligned.m64n96k16.f32.bf16.bf16 "
      "{%0,%1,%2,%3,%4,%5,%6,%7,%8,%9,%10,%11,%12,%13,%14,%15,%16,%17,%18,%19,%20,%21,%22,%23,%24,%25,%26,%27,%28,%29,%30,%31,%32,%33,%34,%35,%36,%37,%38,%39,%40,%41,%42,%43,%44,%45,%46,%47}, "
      "%48, %49, p, 1, 1, 0, 1;\n}\n"
      : "+f"(d[0]), "+f"(d[1]), "+f"(d[2]), "+f"(d[3]), "+f"(d[4]), "+f"(d[5]), "+f"(d[6]), "+f"(d[7]),
        "+f"(d[8]), "+f"(d[9]), "+f"(d[10]), "+f"(d[11]), "+f"(d[12]), "+f"(d[13]), "+f"(d[14]), "+f"(d[15]),
        "+f"(d[16]), "+f"(d[17]), "+f"(d[18]), "+f"(d[19]), "+f"(d[20]), "+f"(d[21]), "+f"(d[22]), "+f"(d[23]),
        "+f"(d[24]), "+f"(d[25]), "+f"(d[26]), "+f"(d[27]), "+f"(d[28]), "+f"(d[29]), "+f"(d[30]), "+f"(d[31]),
        "+f"(d[32]), "+f"(d[33]), "+f"(d[34]), "+f"(d[35]), "+f"(d[36]), "+f"(d[37]), "+f"(d[38]), "+f"(d[39]),
        "+f"(d[40]), "+f"(d[41]), "+f"(d[42]), "+f"(d[43]), "+f"(d[44]), "+f"(d[45]), "+f"(d[46]), "+f"(d[47])
      : "l"(da), "l"(db), "r"(sc));
}

__device__ __forceinline__ void wgmma_ss_n128(float (&d)[64], uint64_t da, uint64_t db, int sc) {
  asm volatile("{\n.reg .pred p;\nsetp.ne.b32 p, %66, 0;\n"
      "wgmma.mma_async.sync.aligned.m64n128k16.f32.bf16.bf16 "
      "{%0,%1,%2,%3,%4,%5,%6,%7,%8,%9,%10,%11,%12,%13,%14,%15,%16,%17,%18,%19,%20,%21,%22,%23,%24,%25,%26,%27,%28,%29,%30,%31,%32,%33,%34,%35,%36,%37,%38,%39,%40,%41,%42,%43,%44,%45,%46,%47,%48,%49,%50,%51,%52,%53,%54,%55,%56,%57,%58,%59,%60,%61,%62,%63}, "
      "%64, %65, p, 1, 1, 0, 1;\n}\n"
      : "+f"(d[0]), "+f"(d[1]), "+f"(d[2]), "+f"(d[3]), "+f"(d[4]), "+f"(d[5]), "+f"(d[6]), "+f"(d[7]),
        "+f"(d[8]), "+f"(d[9]), "+f"(d[10]), "+f"(d[11]), "+f"(d[12]), "+f"(d[13]), "+f"(d[14]), "+f"(d[15]),
        "+f"(d[16]), "+f"(d[17]), "+f"(d[18]), "+f"(d[19]), "+f"(d[20]), "+f"(d[21]), "+f"(d[22]), "+f"(d[23]),
        "+f"(d[24]), "+f"(d[25]), "+f"(d[26]), "+f"(d[27]), "+f"(d[28]), "+f"(d[29]), "+f"(d[30]), "+f"(d[31]),
        "+f"(d[32]), "+f"(d[33]), "+f"(d[34]), "+f"(d[35]), "+f"(d[36]), "+f"(d[37]), "+f"(d[38]), "+f"(d[39]),
        "+f"(d[40]), "+f"(d[41]), "+f"(d[42]), "+f"(d[43]), "+f"(d[44]), "+f"(d[45]), "+f"(d[46]), "+f"(d[47]),
        "+f"(d[48]), "+f"(d[49]), "+f"(d[50]), "+f"(d[51]), "+f"(d[52]), "+f"(d[53]), "+f"(d[54]), "+f"(d[55]),
        "+f"(d[56]), "+f"(d[57]), "+f"(d[58]), "+f"(d[59]), "+f"(d[60]), "+f"(d[61]), "+f"(d[62]), "+f"(d[63])
      : "l"(da), "l"(db), "r"(sc));
}

__device__ __forceinline__ void wgmma_ss_n40(float (&d)[20], uint64_t da, uint64_t db, int sc) {
  asm volatile("{\n.reg .pred p;\nsetp.ne.b32 p, %22, 0;\n"
      "wgmma.mma_async.sync.aligned.m64n40k16.f32.bf16.bf16 "
      "{%0,%1,%2,%3,%4,%5,%6,%7,%8,%9,%10,%11,%12,%13,%14,%15,%16,%17,%18,%19}, "
      "%20, %21, p, 1, 1, 1, 1;\n}\n"
      : "+f"(d[0]), "+f"(d[1]), "+f"(d[2]), "+f"(d[3]), "+f"(d[4]), "+f"(d[5]), "+f"(d[6]), "+f"(d[7]),
        "+f"(d[8]), "+f"(d[9]), "+f"(d[10]), "+f"(d[11]), "+f"(d[12]), "+f"(d[13]), "+f"(d[14]), "+f"(d[15]),
        "+f"(d[16]), "+f"(d[17]), "+f"(d[18]), "+f"(d[19])
      : "l"(da), "l"(db), "r"(sc));
}

__device__ __forceinline__ void wgmma_rs_n8(float (&d)[4], const uint4& a, uint64_t db, int sc) {
  asm volatile("{\n.reg .pred p;\nsetp.ne.b32 p, %9, 0;\n"
      "wgmma.mma_async.sync.aligned.m64n8k16.f32.bf16.bf16 "
      "{%0,%1,%2,%3}, "
      "{%4,%5,%6,%7}, %8, p, 1, 1, 1;\n}\n"
      : "+f"(d[0]), "+f"(d[1]), "+f"(d[2]), "+f"(d[3])
      : "r"(a.x), "r"(a.y), "r"(a.z), "r"(a.w), "l"(db), "r"(sc));
}

__device__ __forceinline__ void wgmma_rs_n16(float (&d)[8], const uint4& a, uint64_t db, int sc) {
  asm volatile("{\n.reg .pred p;\nsetp.ne.b32 p, %13, 0;\n"
      "wgmma.mma_async.sync.aligned.m64n16k16.f32.bf16.bf16 "
      "{%0,%1,%2,%3,%4,%5,%6,%7}, "
      "{%8,%9,%10,%11}, %12, p, 1, 1, 1;\n}\n"
      : "+f"(d[0]), "+f"(d[1]), "+f"(d[2]), "+f"(d[3]), "+f"(d[4]), "+f"(d[5]), "+f"(d[6]), "+f"(d[7])
      : "r"(a.x), "r"(a.y), "r"(a.z), "r"(a.w), "l"(db), "r"(sc));
}

__device__ __forceinline__ void wgmma_rs_n24(float (&d)[12], const uint4& a, uint64_t db, int sc) {
  asm volatile("{\n.reg .pred p;\nsetp.ne.b32 p, %17, 0;\n"
      "wgmma.mma_async.sync.aligned.m64n24k16.f32.bf16.bf16 "
      "{%0,%1,%2,%3,%4,%5,%6,%7,%8,%9,%10,%11}, "
      "{%12,%13,%14,%15}, %16, p, 1, 1, 1;\n}\n"
      : "+f"(d[0]), "+f"(d[1]), "+f"(d[2]), "+f"(d[3]), "+f"(d[4]), "+f"(d[5]), "+f"(d[6]), "+f"(d[7]),
        "+f"(d[8]), "+f"(d[9]), "+f"(d[10]), "+f"(d[11])
      : "r"(a.x), "r"(a.y), "r"(a.z), "r"(a.w), "l"(db), "r"(sc));
}

struct Params {
  const __nv_bfloat16 *logA, *Aim, *Cre, *Cim, *logdt, *Dskip, *x, *wphi, *wo;
  __nv_bfloat16* out;
  uint4* xs;
  long long* ts;
};

__device__ __forceinline__ uint4 tr_row(const uint4 (&v)[8], int i) {
  uint32_t o[4];
#pragma unroll
  for (int m = 0; m < 4; m++) {
    const uint4 &ra = v[2 * m], &rb = v[2 * m + 1];
    const int k = i >> 1;
    const uint32_t xa = k == 0 ? ra.x : k == 1 ? ra.y : k == 2 ? ra.z : ra.w;
    const uint32_t xb = k == 0 ? rb.x : k == 1 ? rb.y : k == 2 ? rb.z : rb.w;
    o[m] = __byte_perm(xa, xb, (i & 1) ? 0x7632 : 0x5410);
  }
  return make_uint4(o[0], o[1], o[2], o[3]);
}

struct cpx { float r, i; };
__device__ __forceinline__ cpx csq(cpx a) { return {a.r * a.r - a.i * a.i, 2.f * (a.r * a.i)}; }
__device__ __forceinline__ cpx polar(float e, float t) {
  const float m = ex2(e);
  return {m * __cosf(t), m * __sinf(t)};
}

struct KgenRaw { uint32_t la, ai, cr, ci; unsigned short ldt; };
__device__ __forceinline__ KgenRaw kgen_load(const Params& P, int d, int unit, int lane) {
  const int o = d * 64 + unit * 32 + lane;
  return {__ldg((const uint32_t*)P.logA + o), __ldg((const uint32_t*)P.Aim + o), __ldg((const uint32_t*)P.Cre + o),
          __ldg((const uint32_t*)P.Cim + o), __ldg((const unsigned short*)P.logdt + d)};
}
struct hc { __half2 r, i; };
struct cpx2 { cpx a, b; };
__device__ __forceinline__ cpx2 csq2(const cpx2& v) { return {csq(v.a), csq(v.b)}; }
__device__ __forceinline__ hc toh(const cpx2& v) { return {__floats2half2_rn(v.a.r, v.b.r), __floats2half2_rn(v.a.i, v.b.i)}; }
__device__ __forceinline__ hc hmul(const hc& z, const hc& w) {
  return {__hfma2(z.r, w.r, __hneg2(__hmul2(z.i, w.i))), __hfma2(z.r, w.i, __hmul2(z.i, w.r))};
}
__device__ __forceinline__ hc hmulc(const hc& z, const hc& w) {
  return {__hfma2(z.r, w.r, __hmul2(z.i, w.i)), __hfma2(z.i, w.r, __hneg2(__hmul2(z.r, w.i)))};
}
__device__ __forceinline__ uint32_t hu(__half2 v) { return *(const uint32_t*)&v; }
__device__ __forceinline__ __half2 uh(uint32_t v) { return *(const __half2*)&v; }

struct KgenAddr { uint32_t sa, lb, lm[4]; };
__device__ __forceinline__ KgenAddr kgen_addr(int lane, uint32_t buf) {
  KgenAddr a;
  a.sa = buf + (lane & 7) * 128 + ((((lane >> 3) ^ lane) & 7) << 4);
  const int q = lane >> 4;
  const uint32_t b = buf + ((lane >> 3) & 1) * 1024 + q * 128;
  a.lb = b + (((lane ^ q) & 7) << 4);
  a.lm[0] = b + (q << 4);
  a.lm[1] = b + ((1 ^ q) << 4);
  a.lm[2] = b + (((2 + (lane & 1)) ^ q) << 4);
  a.lm[3] = b + (((4 + (lane & 3)) ^ q) << 4);
  asm volatile("" : "+r"(a.sa), "+r"(a.lb), "+r"(a.lm[0]), "+r"(a.lm[1]), "+r"(a.lm[2]), "+r"(a.lm[3]));
  return a;
}
__device__ __forceinline__ void kgen_unit(const KgenRaw& r, const KgenAddr& ad, uint32_t zero, float (&k)[5][4], float& k2048, float& sc) {
  const float dt = bf_round(expf(bf_lo(r.ldt)));
  const uint32_t ar = pack_bf(ex2(bf_lo(r.la) * 1.4426950408889634f), ex2(bf_hi(r.la) * 1.4426950408889634f));
  const float ca = dt * -1.4426950408889634f, a0 = bf_lo(ar) * ca, a1 = bf_hi(ar) * ca;
  const float f0 = bf_lo(r.ai) * dt, f1 = bf_hi(r.ai) * dt;
  const float r0 = f0 * 20.21267777267071f, r1 = f1 * 20.21267777267071f;
  const uint32_t cm = __vmaxu2(r.cr & 0x7fff7fffu, r.ci & 0x7fff7fffu);
  const uint32_t ex = min(max(__reduce_max_sync(0xffffffffu, max(cm >> 16, cm & 0xffffu)) >> 7, 1u), 253u);
  const float cs = uf((254u - ex) << 23);
  sc = 2.f * dt * uf(ex << 23);
  const cpx2 C = {{bf_lo(r.cr) * cs, bf_lo(r.ci) * -cs}, {bf_hi(r.cr) * cs, bf_hi(r.ci) * -cs}};
  auto put = [&](const hc (&v)[8]) {
    stsm4(ad.sa, hu(v[0].r), hu(v[1].r), hu(v[2].r), hu(v[3].r));
    stsm4(ad.sa + 1024, hu(v[0].i), hu(v[1].i), hu(v[2].i), hu(v[3].i));
    stsm4(ad.sa ^ 64, hu(v[4].r), hu(v[5].r), hu(v[6].r), hu(v[7].r));
    stsm4((ad.sa ^ 64) + 1024, hu(v[4].i), hu(v[5].i), hu(v[6].i), hu(v[7].i));
    __syncwarp();
  };
  auto get = [&](uint32_t (&o)[4][4], uint32_t a) {
#pragma unroll
    for (int i = 0; i < 4; i++) ldsm4(o[i], (a ^ (i << 5)) + i * 256);
  };
  auto at = [](const uint32_t (&o)[4][4], int s) { return hc{uh(o[s >> 1][2 * (s & 1)]), uh(o[s >> 1][2 * (s & 1) + 1])}; };
  uint32_t A[8][4];
  auto tile = [&](int j, const uint32_t (&B)[4][4]) {
    k[j][0] = k[j][1] = k[j][2] = k[j][3] = 0.f;
#pragma unroll
    for (int s = 0; s < 8; s++) mma_h(k[j], A[s], B[s >> 1][2 * (s & 1)], B[s >> 1][2 * (s & 1) + 1]);
  };
  auto after = [&](cpx2 v, uint32_t dep) { v.a.r = uf(fu(v.a.r) ^ (dep & zero)); v.b.r = uf(fu(v.b.r) ^ (dep & zero)); return v; };
  const cpx2 w1 = {polar(a0, f0), polar(a1, f1)};
  const cpx2 w127 = {polar(a0 * 127.f, (r0 - rintf(r0)) * 6.283185307179586f), polar(a1 * 127.f, (r1 - rintf(r1)) * 6.283185307179586f)};
  const cpx2 w2 = csq2(w1), w4 = csq2(w2);
  uint32_t T0[4][4], X[4][4], M[3][4][4];
  {
    hc t[8];
    t[0] = {uh(0x3C003C00u), uh(0u)}; t[1] = toh(w1); t[2] = toh(w2); t[4] = toh(w4);
    t[3] = hmul(t[1], t[2]); t[5] = hmul(t[1], t[4]); t[6] = hmul(t[2], t[4]); t[7] = hmul(t[3], t[4]);
    put(t); get(T0, ad.lb);
  }
  const cpx2 w8 = csq2(w4), w16 = csq2(w8), w32 = csq2(w16), w64 = csq2(w32);
  {
    const hc m8 = toh(w8), m16 = toh(w16), m32 = toh(w32);
    hc a[8];
    a[0] = toh(C); a[1] = hmulc(a[0], m8);
    a[2] = hmulc(a[0], m16); a[3] = hmulc(a[1], m16);
#pragma unroll
    for (int i = 0; i < 4; i++) a[4 + i] = hmulc(a[i], m32);
    put(a); get(X, ad.lb);
  }
  const cpx2 w127b = KG_AFTER ? after(w127, T0[0][0]) : w127;
  const cpx2 w128 = {{w127b.a.r * w1.a.r - w127b.a.i * w1.a.i, w127b.a.r * w1.a.i + w127b.a.i * w1.a.r},
                     {w127b.b.r * w1.b.r - w127b.b.i * w1.b.i, w127b.b.r * w1.b.i + w127b.b.i * w1.b.r}};
  const cpx2 w256 = csq2(w128), w512 = csq2(w256);
  const hc m128 = toh(w128), m256 = toh(w256), m512 = toh(w512);
  {
    const hc m254 = toh(csq2(w127b)), m127 = toh(w127b);
    hc m[8];
    m[0] = toh(w64); m[1] = m128; m[2] = m256; m[3] = hmul(m127, m256);
    m[4] = m512; m[5] = hmul(m127, m512); m[6] = hmul(m[4], m254); m[7] = hmul(m[5], m254);
    put(m);
    get(M[0], ad.lm[0]);
#pragma unroll
    for (int s = 0; s < 8; s++) {
      const hc z = at(X, s), y = hmulc(z, at(M[0], s));
      A[s][0] = hu(z.r) + zero; A[s][1] = hu(y.r); A[s][2] = hu(z.i) + zero; A[s][3] = hu(y.i);
    }
#pragma unroll
    for (int i = 0; i < 3; i++) get(M[i], ad.lm[i + 1]);
  }
  tile(0, T0);
  const cpx2 w1024 = csq2(KG_AFTER ? after(w512, X[0][0]) : w512), we = csq2(w1024);
  {
    hc t[8];
    t[0] = toh(w1024); t[1] = hmul(t[0], m128);
    t[2] = hmul(t[0], m256); t[3] = hmul(t[1], m256);
#pragma unroll
    for (int i = 0; i < 4; i++) t[4 + i] = hmul(t[i], m512);
    put(t); get(X, ad.lb);
  }
  k2048 = (C.a.r * we.a.r + C.a.i * we.a.i + C.b.r * we.b.r + C.b.i * we.b.i) * sc;
#pragma unroll
  for (int j = 1; j < 5; j++) k[j][0] = k[j][1] = k[j][2] = k[j][3] = 0.f;
#pragma unroll
  for (int s = 0; s < 8; s++) {
#pragma unroll
    for (int j = 0; j < 3; j++) {
      const hc y = hmul(at(T0, s), at(M[j], s));
      mma_h(k[1 + j], A[s], hu(y.r), hu(y.i));
    }
    mma_h(k[4], A[s], X[s >> 1][2 * (s & 1)], X[s >> 1][2 * (s & 1) + 1]);
  }
}

__device__ __forceinline__ void build_tables(uint32_t tb, int lane, float (&k)[5][4], float k2048) {
  const int g = lane >> 2, c = lane & 3;
  const uint32_t kc = tb + T_KC + 16;
  {
    const uint32_t a0 = kc + 16 * g + 4 * c, a2 = kc + 2 * (256 + 4 * g + c);
    const uint32_t a3 = kc + 2 * (384 + 2 * g + 64 * (c & 1) + (c >> 1)), a4 = kc + 2 * (512 + g + 32 * c);
#pragma unroll
    for (int r = 0; r < 2; r++) {
      sts32(a0 + 128 * r, pack_bf(k[0][2 * r], k[0][2 * r + 1]));
      sts32(a0 + 128 * r + 256, pack_bf(k[1][2 * r], k[1][2 * r + 1]));
      const uint32_t w2 = pack_bf(k[2][2 * r], k[2][2 * r + 1]);
      const uint32_t w3 = pack_bf(k[3][2 * r], k[3][2 * r + 1]);
      const uint32_t w4 = pack_bf(k[4][2 * r], k[4][2 * r + 1]);
      sts16(a2 + 64 * r, w2); sts16(a2 + 64 * r + 128, w2 >> 16);
      sts16(a3 + 32 * r, w3); sts16(a3 + 32 * r + 64, w3 >> 16);
      sts16(a4 + 16 * r, w4); sts16(a4 + 16 * r + 32, w4 >> 16);
    }
  }
  if (lane == 0) { sts16(kc + 2 * 640, pack_bf(k2048, 0.f)); sts32(kc - 4, 0); }
  __syncwarp();
  const uint32_t td = tb + T_D + 32;
#pragma unroll
  for (int hf = 0; hf < 2; hf++) {
    const uint2 v = lds64(kc + 256 * hf + 8 * lane);
    const uint32_t pv = lds32(kc + 256 * hf + 8 * lane - 4);
    sts128(td + 512 * hf + 16 * lane, __byte_perm(v.x, pv, 0x7610), __byte_perm(v.x, v.x, 0x1032), __byte_perm(v.y, v.x, 0x7610),
           __byte_perm(v.y, v.y, 0x1032));
  }
#pragma unroll
  for (int hf = 0; hf < 2; hf++) {
    const uint32_t v = lds32(kc + 512 + 128 * hf + 4 * lane), nx = lds32(kc + 516 + 128 * hf + 4 * lane);
    uint32_t w0 = __byte_perm(v, v, 0x1010);
    const uint32_t w1 = w0;
    if (hf == 0) { const uint32_t pv = lds32(kc + 508); if (lane == 0) w0 = __byte_perm(v, pv, 0x7610); }
    sts128(td + 1024 + 512 * hf + 16 * lane, w0, w1, __byte_perm(v, v, 0x1032), __byte_perm(nx, v, 0x7610));
  }
  {
    const uint32_t kk = lds16(kc + 2 * 384);
    const uint32_t w = lane < 3 ? (kk | (kk << 16)) : (lane == 3 ? (kk << 16) : 0u);
    if (lane < 24) sts32(td + 4 * (lane < 16 ? 512 + lane : lane - 24), w);
    const uint32_t lo_ = lds16(kc + 2 * 511), le_ = lds16(kc + 2 * 512);
    const uint32_t ja = tb + T_5 + (lane < 16 ? 4 * lane : 256 + 4 * lane);
    sts32(ja, lane == 16 ? (le_ << 16) : 0u);
    sts32(ja + 384, lane == 16 ? (lo_ << 16) : 0u);
    sts32(tb + (lane < 16 ? T_7 : T_9 - 64) + 4 * lane, 0u);
  }
#pragma unroll
  for (int s = 0; s < 2; s++) {
    const uint32_t b = kc + 2 * (s ? 512 : 384) + 8 * lane;
    const uint2 v = lds64(b);
    uint32_t em = lds16(b - 2), e0 = v.x;
    const uint32_t e4 = lds16(b + 8);
    if (lane == 0) { em = 0; e0 = 0; }
    sts64(tb + (s ? T_7 : T_3) + 64 + 8 * lane, __byte_perm(v.x, em, 0x5432), __byte_perm(v.y, v.x, 0x7632));
    sts64(tb + (s ? T_9 : T_5) + 64 + 8 * lane, __byte_perm(v.y, e0, 0x5410), __byte_perm(e4, v.y, 0x5410));
  }
  __syncwarp();
}

__device__ __forceinline__ uint32_t box2w(int lo, int n, int o) {
  return ((unsigned)(o - lo) < (unsigned)n ? 0x3F80u : 0u) | ((unsigned)(o + 1 - lo) < (unsigned)n ? 0x3F800000u : 0u);
}

__device__ __forceinline__ void conv_channel(uint32_t ub, uint32_t tb, int lane, uint4* ydst) {
  const int g = lane >> 2, c = lane & 3, x = g - 2 * c;
  const int mi = lane >> 3;
  const uint32_t qa = ub + U_PAD + 16 * (lane & 7) + ((mi == 0 || mi == 3) ? U_ODD : 0) - (mi == 0 ? 16 : 0);
  const uint32_t hb = ub + U_PAD + (mi & 1) * U_ODD + 16 * ((lane >> 4) + (lane & 7)) - 16;
  const uint32_t kv = lds16(tb + T_KC + 16 + 2 * 512);
  const int oh = c < 2 ? 8 + 2 * c : 2 * c - 8, og = c < 3 ? 2 * c : -10;
  uint32_t bx[4] = {box2w(g - 4, 9, 2 * c), box2w(g - 3, 7, 2 * c), box2w(g - 4, 9, oh), box2w(g - 3, 7, oh)};
  uint32_t by[4] = {box2w(g - 10, 5, 2 * c - 8), box2w(g - 5, 3, 2 * c - 8), box2w(g - 10, 5, og), box2w(g - 5, 3, og)};
  uint32_t lb0 = ((unsigned)(x + 5) < 2u ? kv : 0u) | ((unsigned)(x + 4) < 2u ? kv << 16 : 0u);
  uint32_t lb1 = ((unsigned)(x - 3) < 2u ? kv : 0u) | ((unsigned)(x - 4) < 2u ? kv << 16 : 0u);
  const int q0 = g - 1, q1 = c < 3 ? g : g - 2;
  uint32_t y0a = ub + U_PAD + (q0 & 1) * U_ODD + 16 * (q0 >> 1) + 4 * c;
  uint32_t y1a = ub + U_PAD + (q1 & 1) * U_ODD + 16 * (q1 >> 1) + 4 * c;
#pragma unroll
  for (int i = 0; i < 4; i++) asm volatile("" : "+r"(bx[i]), "+r"(by[i]));
  asm volatile("" : "+r"(lb0), "+r"(lb1), "+r"(y0a), "+r"(y1a));
  mbar_wait(BAR(MB_UFULL));
  mbar_spin(BAR(MB_EMPTY + 15));
  TS(36);
  float acc[16][4];
  {
    uint32_t z09[8], z07[8], zm9[8], zm7[8];
#pragma unroll
    for (int i = 0; i < 8; i++) {
      uint32_t h[4];
      ldsm4(h, hb + 128 * i);
      float y0, y1, y2, y3, w0, w1, w2, w3;
      mma0(y0, y1, y2, y3, bx[0], bx[1], bx[2], bx[3], h[2], c < 2 ? h[3] : h[1]);
      mma0(w0, w1, w2, w3, bx[0], bx[1], bx[2], bx[3], h[1], c < 2 ? h[2] : h[0]);
      z09[i] = pack_bf(y0, y1); z07[i] = pack_bf(y2, y3);
      zm9[i] = pack_bf(w0, w1); zm7[i] = pack_bf(w2, w3);
    }
  uint32_t f3[3][4][4];
  {
    const uint32_t fa = tb + T_7 + 4 * (16 + x);
#pragma unroll
    for (int tt = 0; tt < 3; tt++)
#pragma unroll
      for (int D = 0; D < 4; D++) {
        const uint32_t a = fa + (tt == 0 ? 316 : (tt == 1 ? 320 : 0)) + 64 * D;
        f3[tt][D][0] = lds32(a); f3[tt][D][1] = lds32(a + 32); f3[tt][D][2] = lds32(a - 32); f3[tt][D][3] = lds32(a);
      }
  }
    SPLIT();
    nb_sync(NB_GATE, 256);
    SPLIT();
    float a[4][2][4];
#pragma unroll
    for (int kap = 0; kap < 4; kap++)
#pragma unroll
      for (int sg = 0; sg < 2; sg++)
#pragma unroll
        for (int bk = 3; bk >= kap; bk--) {
          const uint32_t(&q0_)[4] = f3[sg ? 2 : 0][bk - kap];
          const uint32_t(&q1_)[4] = f3[sg ? 2 : 1][bk - kap];
          float(&a0)[4] = a[bk][0];
          float(&a1)[4] = a[bk][1];
          if (sg == 0 && kap == 0) {
            mma0(a0[0], a0[1], a0[2], a0[3], q0_[0], q0_[1], q0_[2], q0_[3], z09[0], z09[1]);
            mma0(a1[0], a1[1], a1[2], a1[3], q1_[0], q1_[1], q1_[2], q1_[3], zm9[0], zm9[1]);
          } else {
            mma(a0[0], a0[1], a0[2], a0[3], q0_[0], q0_[1], q0_[2], q0_[3], sg ? zm7[2 * kap] : z09[2 * kap], sg ? zm7[2 * kap + 1] : z09[2 * kap + 1]);
            mma(a1[0], a1[1], a1[2], a1[3], q1_[0], q1_[1], q1_[2], q1_[3], sg ? z07[2 * kap] : zm9[2 * kap], sg ? z07[2 * kap + 1] : zm9[2 * kap + 1]);
          }
        }
    SPLIT();
#pragma unroll
    for (int i = 0; i < 8; i++) {
      uint32_t h[4];
      ldsm4(h, qa + 128 * i);
      const float ci[4] = {a[i >> 1][0][2 * (i & 1)], a[i >> 1][0][2 * (i & 1) + 1], a[i >> 1][1][2 * (i & 1)], a[i >> 1][1][2 * (i & 1) + 1]};
      mmac(acc[8 + i], h[0], h[1], h[2], h[3], lb0, lb1, ci);
    }
  }
  TS(44);
  {
    uint2 a5[10], a3[10];
    const uint32_t aa = tb + T_5 + 4 * (8 + 2 * g - 2 * c);
#pragma unroll
    for (int m = 0; m < 10; m++) { a5[m] = lds64(aa + 32 * m); a3[m] = lds64(aa + 384 + 32 * m); }
    uint32_t x5[12][2], x3[12][2];
    auto ygen = [&](int kap) {
#pragma unroll
      for (int hh = 0; hh < 2; hh++) {
        float y0, y1, y2, y3;
        mma0(y0, y1, y2, y3, by[0], by[1], by[2], by[3], lds32(y0a + 128 * kap + 64 * hh), lds32(y1a + 128 * kap + 64 * hh));
        x5[kap][hh] = pack_bf(y0, y1);
        x3[kap][hh] = pack_bf(y2, y3);
      }
    };
    ygen(11); ygen(10); ygen(9); ygen(8);
#pragma unroll
    for (int kap = 11; kap >= 0; kap--) {
      if (kap >= 4) ygen(kap - 4);
#pragma unroll
      for (int sg = 0; sg < 2; sg++)
#pragma unroll
        for (int i = 4; i >= 0; i--) {
          const int be = kap + 4 + i;
          if (be <= 15) {
            const uint2 &hi = sg ? a3[2 * i + 1] : a5[2 * i + 1], &lo = sg ? a3[2 * i] : a5[2 * i];
            const uint32_t b0 = sg ? x3[kap][0] : x5[kap][0], b1 = sg ? x3[kap][1] : x5[kap][1];
            if (be < 8 && i == 0 && sg == 0) mma0(acc[be][0], acc[be][1], acc[be][2], acc[be][3], hi.x, hi.y, lo.x, lo.y, b0, b1);
            else mma(acc[be][0], acc[be][1], acc[be][2], acc[be][3], hi.x, hi.y, lo.x, lo.y, b0, b1);
          }
        }
    }
  }
  TS(45);
  {
    const uint32_t st = tb + T_ST + lane * 8;
#pragma unroll
    for (int be = 4; be < 12; be++) sts64(st + 256 * be, pack_bf(acc[be][0], acc[be][1]), pack_bf(acc[be][2], acc[be][3]));
    SPLIT();
    uint32_t F[66], qd[8][4];
    const uint32_t fa = tb + T_D + 32 + 4 * x;
#pragma unroll
    for (int i = 0; i < 32; i++) {
      const int s = 120 - (i >> 2) - 8 * (i & 3);
      uint32_t(&q)[4] = qd[i & 7];
      ldsm4(q, qa + 16 * s);
      const int m = 16 * (i & 3) + 2 * (i >> 2);
      F[m] = lds32(fa + 32 * m); F[m + 1] = lds32(fa + 32 * m + 32);
#pragma unroll
      for (int be = 15; be >= 12; be--) {
        const int de = 8 * be - s;
        float(&a)[4] = (be >= 14 && !(i & 1)) ? acc[be - 4] : acc[be];
        if (de >= 0 && be >= 14 && i == 2 * (15 - be)) mma0(a[0], a[1], a[2], a[3], q[0], q[1], q[2], q[3], F[2 * de + 1], F[2 * de]);
        else if (de >= 0) mma(a[0], a[1], a[2], a[3], q[0], q[1], q[2], q[3], F[2 * de + 1], F[2 * de]);
      }
    }
#pragma unroll
    for (int i = 0; i < 8; i++) acc[14 + (i >> 2)][i & 3] += acc[10 + (i >> 2)][i & 3];
    F[64] = lds32(fa + 32 * 64); F[65] = lds32(fa + 32 * 65);
#pragma unroll
    for (int i = 0; i < 6; i++) ldsm4(qd[i], qa + 128 * 11 - 16 * i);
    uint2 sv = lds64(st + 256 * 11);
    float ci[4] = {bf_lo(sv.x), bf_hi(sv.x), bf_lo(sv.y), bf_hi(sv.y)};
    float T[5][4];
#pragma unroll
    for (int i = 0; i < 16; i++) T[i >> 2][i & 3] = acc[12 + (i >> 2)][i & 3];
    nb_sync(NB_YZ, 160);
    TS(46);
    uint32_t held[2];
#pragma unroll
    for (int be = 11; be >= 0; be--) {
      if (be & 1) SPLITN(be);
      const uint32_t qp = qa + 128 * be;
#pragma unroll
      for (int k = 4; k >= 1; k--) mmac(T[k], qd[0][0], qd[0][1], qd[0][2], qd[0][3], F[16 * k + 1], F[16 * k], T[k - 1]);
      if (be >= 4) mmac(T[0], qd[0][0], qd[0][1], qd[0][2], qd[0][3], F[1], F[0], ci);
      else mma0(T[0][0], T[0][1], T[0][2], T[0][3], qd[0][0], qd[0][1], qd[0][2], qd[0][3], F[1], F[0]);
      ldsm4(qd[6], qp - 16 * 6);
      ldsm4(qd[7], qp - 16 * 7);
      if (be > 4) sv = lds64(st + 256 * (be - 1));
#pragma unroll
      for (int i = 1; i < 8; i++) {
#pragma unroll
        for (int k = 3; k >= 0; k--)
          mma(T[k][0], T[k][1], T[k][2], T[k][3], qd[i][0], qd[i][1], qd[i][2], qd[i][3], F[16 * k + 2 * i + 1], F[16 * k + 2 * i]);
        if (i < 7 && be > 0) ldsm4(qd[i - 1], qp - 128 - 16 * (i - 1));
        if (i == 2) {
          const uint32_t w0 = pack_bf(T[4][0], T[4][1]), w1 = pack_bf(T[4][2], T[4][3]);
          if (be & 1) { held[0] = w0; held[1] = w1; }
          else st_x(ydst + (be + 4) * 16, nz(w0), w1, held[0], held[1]);
          if ((be & 3) == 3 && be < 11) nb_arrive(NB_Y + 2 + (be >> 2), 160);
        }
        if (i == 4 && be > 4) { ci[0] = bf_lo(sv.x); ci[1] = bf_hi(sv.x); ci[2] = bf_lo(sv.y); ci[3] = bf_hi(sv.y); }
      }
    }
    nb_arrive(NB_Y + 1, 160);
#pragma unroll
    for (int B = 1; B >= 0; B--)
      st_x(ydst + B * 32, nz(pack_bf(T[2 * B][0], T[2 * B][1])), pack_bf(T[2 * B][2], T[2 * B][3]),
           pack_bf(T[2 * B + 1][0], T[2 * B + 1][1]), pack_bf(T[2 * B + 1][2], T[2 * B + 1][3]));
  }
}

__device__ __forceinline__ void dual_exp(const uint32_t* w, uint32_t* e) {
  const float L = 1.44268798828125f;
  uint32_t mx = bmax2(bmax2(w[0], w[1]), bmax2(w[2], w[3]));
  uint32_t mn = bmin2(bmin2(w[0], w[1]), bmin2(w[2], w[3]));
  mx = bmax2(mx, __shfl_xor_sync(0xffffffffu, mx, 1));
  mn = bmin2(mn, __shfl_xor_sync(0xffffffffu, mn, 1));
  mx = bmax2(mx, __shfl_xor_sync(0xffffffffu, mx, 2));
  mn = bmin2(mn, __shfl_xor_sync(0xffffffffu, mn, 2));
  const float mx0 = bf_lo(mx) * -L, mx1 = bf_hi(mx) * -L, mn0 = bf_lo(mn) * L, mn1 = bf_hi(mn) * L;
#pragma unroll
  for (int i = 0; i < 2; i++) {
    const float a0 = bf_lo(w[2 * i]), a1 = bf_hi(w[2 * i]), b0 = bf_lo(w[2 * i + 1]), b1 = bf_hi(w[2 * i + 1]);
    e[2 * i] = pack_bf(ex2(fmaf(a0, L, mx0)), ex2(fmaf(b0, L, mx0)));
    e[2 * i + 1] = pack_bf(ex2(fmaf(a1, L, mx1)), ex2(fmaf(b1, L, mx1)));
    e[4 + 2 * i] = pack_bf(ex2(fmaf(a0, -L, mn0)), ex2(fmaf(b0, -L, mn0)));
    e[5 + 2 * i] = pack_bf(ex2(fmaf(a1, -L, mn1)), ex2(fmaf(b1, -L, mn1)));
  }
}
__device__ __forceinline__ void normalise(uint32_t* e, const float (&s)[4]) {
  const uint32_t r = pack_bf(rcp(s[0]), rcp(s[2]));
  const __nv_bfloat162 rr = *(const __nv_bfloat162*)&r;
#pragma unroll
  for (int i = 0; i < 4; i++) {
    const __nv_bfloat162 v = __hmul2(*(const __nv_bfloat162*)&e[i], (i & 1) ? __high2bfloat162(rr) : __low2bfloat162(rr));
    e[i] = *(const uint32_t*)&v;
  }
}
__host__ __device__ constexpr uint64_t qdesc(uint32_t addr) { return mkdesc(addr, 128, 256, 0); }

__global__ void __launch_bounds__(NTHREADS, 1)
fused_kernel(const Params P, const __grid_constant__ CUtensorMap mx, const __grid_constant__ CUtensorMap mw,
             const __grid_constant__ CUtensorMap mo, const __grid_constant__ CUtensorMap mu,
             const __grid_constant__ CUtensorMap mout) {
  constexpr uint32_t sb = SB;
  const int tid = threadIdx.x, lane = tid & 31;
  const int warp = __shfl_sync(0xffffffffu, tid >> 5, 0);
  const int b = blockIdx.x, oct = b >> 3, i8 = b & 7;
  const int rt = (((oct & 4) ? ~oct : oct) & 3) * 2 + (i8 >> 2);
  const int hp = (oct >> 2) * 4 + (i8 & 3);

  const int wg = warp >> 2, w = warp & 3;
  const int d = b * 4 + ((tid >> 5) & 3);
  KgenRaw raw = {0, 0, 0, 0, 0};
  if (tid >= 128) raw = kgen_load(P, d, (tid >> 7) & 1, lane);
  const unsigned short dsk = __ldg((const unsigned short*)P.Dskip + d);
  const uint32_t tb = sb + OFF_T + w * T_CH;
  if (warp >= 12) {
    asm volatile("setmaxnreg.dec.sync.aligned.u32 32;");
    if (warp == 12) {
      if (lane == 0) {
#pragma unroll
        for (int i = 0; i < 9; i++) mbar_init(BAR(i), 1);
        asm volatile("fence.mbarrier_init.release.cluster;" ::: "memory");
      }
      __syncwarp();
      if (lane < 9) mbar_expect(BAR(0) + 8 * lane, lane == 0 ? 16384 : 28672);
      __syncwarp();
      nb_arrive(NB_PROD, 384);
#pragma unroll 1
      for (int kb = 0; kb < 8; kb++) {
        if (kb == U_AT) e_tma4d(sb + OFF_STG0, &mu, BAR(MB_URAW), i8 * 64, oct * 2);
        e_tma3d(sb + OFF_W + kb * 12288, &mw, BAR(MB_FULL) + 8 * kb, hp * 32, kb * 64, 0);
        if (kb < 5) e_tma2d(sb + OFF_X + (kb < 2 ? kb + 3 : kb - 2) * 16384, &mx, BAR(MB_FULL) + 8 * kb, kb * 64, rt * 256);
      }
      if (smem_u32(smem_raw) != SB) __trap();
      if (lane == 0) TS1(54);
      nb_sync(NB_GATE + 1, 64);
      if (X2_AT < 0) e_prefetch(P.x + (size_t)(rt * 256 + 128 + hp * 8) * 512, 8192);
      uint32_t slot = sb + OFF_X + 3 * 16384;
#pragma unroll 1
      for (int n = 0; n < 11; n++) {
        mbar_spin(BAR(MB_EMPTY) + 8 * n);
        const int m = n + 5;
        e_tma2d(slot, &mx, BAR(MB_FULL) + 8 * m, (m & 7) * 64, rt * 256 + (m >> 3) * 128);
        slot = slot == sb + OFF_X + 4 * 16384 ? sb + OFF_X : slot + 16384;
        if (n == X2_AT) e_prefetch(P.x + (size_t)(rt * 256 + 128 + hp * 8) * 512, 8192);
        if (n == 7) {
          e_prefetch(P.wo + (size_t)b * 2048, 4096);
          asm volatile("prefetch.tensormap [%0];" ::"l"(&mo) : "memory");
          asm volatile("prefetch.tensormap [%0];" ::"l"(&mout) : "memory");
        }
      }
#pragma unroll 1
      for (int i = 0; i < 8; i++) {
        mbar_wait(BAR(MB_EMPTY + 10) + 8 * ((0x54332222u >> (4 * i)) & 7));
        const int w0 = (0x54736210u >> (4 * i)) & 7;
        e_tma3d(sb + OFF_W + w0 * 16384, &mo, BAR(MB_WO), 0, w0 * 64, (hp & 3) * 2);
      }
    } else {
      if (warp == 13) {
        if (lane == 0) {
#pragma unroll
          for (int i = 9; i < 40; i++) mbar_init(BAR(i), i < MB_EMPTY ? 1 : 4);
          asm volatile("fence.mbarrier_init.release.cluster;" ::: "memory");
        }
        __syncwarp();
        if (lane < 14 && lane != 9) mbar_expect(BAR(MB_FULL + 8) + 8 * lane, lane == 8 ? 131072 : (lane == 10 ? 8192 : (lane == 13 ? 24576 : 16384)));
        nb_arrive(NB_GATE + 1, 64);
      } else if (warp == 14) {
        asm volatile("prefetch.tensormap [%0];" ::"l"(&mw) : "memory");
        asm volatile("prefetch.tensormap [%0];" ::"l"(&mx) : "memory");
        asm volatile("prefetch.tensormap [%0];" ::"l"(&mu) : "memory");
        e_prefetch(P.x + (size_t)(rt * 256 + hp * 8) * 512, 8192);
      }
      nb_sync(NB_PROD, 384);
      if (warp == 15) {
        const uint4 v0 = __ldg((const uint4*)P.wphi + hp * 64 + lane), v1 = __ldg((const uint4*)P.wphi + hp * 64 + 32 + lane);
        sts128(sb + OFF_PHI + (lane & 1) * 256 + (lane >> 1) * 16, v0.x, v0.y, v0.z, v0.w);
        sts128(sb + OFF_PHI + 512 + (lane & 1) * 256 + (lane >> 1) * 16, v1.x, v1.y, v1.z, v1.w);
        const uint32_t one = (((lane >> 3) ^ (lane >> 4)) & 1) ? 0u : ((lane & 1) ? 0x3F800000u : 0x3F80u);
        const int q = (lane >> 1) & 3;
        sts128(sb + OFF_EYE + lane * 16, q == 0 ? one : 0u, q == 1 ? one : 0u, q == 2 ? one : 0u, q == 3 ? one : 0u);
        sts64(sb + OFF_ONE + lane * 8, 0x3F803F80u, 0x3F803F80u);
        asm volatile("fence.proxy.async.shared::cta;" ::: "memory");
        nb_arrive(NB_KREAD, 160);
      }
      uint32_t* cnt = (uint32_t*)(P.xs + X_CNT) + (warp == 13 ? i8 : (warp == 14 ? 8 + rt : 16 + oct)) * 32;
      const unsigned target = (ld_x32(cnt) & ~15u) + 16;
      if (warp != 14) {
        if (warp == 15) mbar_wait(BAR(MB_EMPTY + ZERO_STEP));
        uint4* pz = P.xs + (warp == 13 ? X_PART + (hp * 8 + rt) * 144 : X_Y + b * 1024) + lane;
#pragma unroll 1
        for (int i = (warp == 13 ? 144 : 1024) - lane; i > 0; i -= 32, pz += 32) st_x(pz, 0, 0, 0, 0);
      }
      if (warp == 15) __syncwarp();
      else nb_sync(warp == 13 ? NB_INIT : NB_ODONE, warp == 13 ? 160 : 288);
      if (lane == 0) asm volatile("red.release.gpu.global.add.u32 [%0], %1;" ::"l"(cnt), "r"(warp == 15 ? 2 : 1) : "memory");
      if (lane == 0) TS1(warp == 13 ? 50 : (warp == 14 ? 57 : 53));
      __syncwarp();
      if (warp == 14) nb_arrive(NB_GATE + 1, 160);
      asm volatile("fence.proxy.async.shared::cta;" ::: "memory");
      if (warp == 13) cnt += ((lane & 1 ? b >> 4 : i8 ^ (lane & 4)) - i8) * 32;
#pragma unroll 1
      for (int i = 0; i < SPIN_MAX; i++) {
        unsigned v;
        asm volatile("ld.acquire.gpu.global.u32 %0, [%1];" : "=r"(v) : "l"(cnt) : "memory");
        if (__all_sync(0xffffffffu, (int)(v - target) >= 0)) break;
      }
      if (lane == 0) TS1(warp == 13 ? 51 : (warp == 14 ? 58 : 55));
      if (warp == 15) { nb_arrive(NB_YZ, 160); return; }
      asm volatile("fence.proxy.async.global;" ::: "memory");
      if (warp == 13) {
        mbar_wait(BAR(MB_EMPTY + 11));
        e_expect(BAR(MB_UFULL), 4 * U_CH);
        e_bulk(sb + OFF_U, P.xs + X_UT + b * (U_CH / 4), 4 * U_CH, BAR(MB_UFULL));
      } else {
        const uint4* src = P.xs + X_O + (rt * 4 + (hp >> 2)) * 4096;
        e_bulk(sb + OFF_X + 32768 + 57344, src + 3584, 8192, BAR(MB_O));
        e_bulk(sb + OFF_X + 32768, src, 16384, BAR(MB_O + 1));
        e_bulk(sb + OFF_X + 49152, src + 1024, 16384, BAR(MB_O + 2));
        e_bulk(sb + OFF_STG0, src + 3200, 6144, BAR(MB_O + 3));
        nb_sync(NB_BDONE, 288);
        asm volatile("fence.proxy.async.shared::cta;" ::: "memory");
        e_bulk(sb + OFF_U, src + 2048, 18432, BAR(MB_O + 3));
      }
    }
    return;
  }

  asm volatile("setmaxnreg.inc.sync.aligned.u32 160;");
  const int t = tid & 127;
  const int g = lane >> 2, c = lane & 3;
  const uint32_t kp = wg ? ((tb + 127) & ~127u) + (wg & 1) * 2048 : sb + OFF_STG0 + 16384;
  const KgenAddr kad = kgen_addr(lane, kp);
  if (wg) nb_sync(NB_PROD, 384);
  float k[5][4], k2048, ksc;
  if (wg || (WARM_K && w == 1)) {
    kgen_unit(raw, kad, blockIdx.y, k, k2048, ksc);
    TS(40 + wg);
    if ((fu(k[0][0]) & fu(k[1][0]) & fu(k[2][0]) & fu(k[3][0]) & fu(k[4][0])) == 0xffffffffu) sts32(kp, 0);
  }
  if (wg) nb_arrive(0, 384);
  if (wg) {
    if (wg == 1) {
      uint32_t h[10];
#pragma unroll
      for (int j = 0; j < 10; j++) h[j] = hu(__floats2half2_rn(k[j >> 1][2 * (j & 1)], k[j >> 1][2 * (j & 1) + 1]));
      sts128(kp + lane * 16, h[0], h[1], h[2], h[3]);
      sts128(kp + 512 + lane * 16, h[4], h[5], h[6], h[7]);
      sts128(kp + 1024 + lane * 16, h[8], h[9], fu(k2048), fu(ksc));
      nb_arrive(NB_PREP, 256);
    }
  } else {
    nb_sync(NB_KREAD, 160);
    nb_sync(0, 384);
  }
  if (wg == 1) {
    mbar_wait(BAR(MB_URAW));
    TS(48);
    uint4* dst = P.xs + X_UT + (i8 * 64 + g) * (U_CH / 16) + (w & 1) * (U_ODD / 16) + U_PAD / 16 + oct * 8 + (w >> 1) * 4 + c;
    const int ln = ((lane >> 1) & 3) + 4 * (lane & 1);
    uint32_t r[8][4];
#pragma unroll
    for (int i = 0; i < 8; i++) ldsm4t(r[i], sb + OFF_STG0 + w * 4096 + ((lane >> 3) * 8 + ln) * 128 + ((i ^ ln) << 4));
#pragma unroll
    for (int i = 0; i < 8; i++) dst[i * (U_CH / 2)] = make_uint4(r[i][0], r[i][1], r[i][2], r[i][3]);
    nb_arrive(NB_INIT, 160);
    if (lane == 0) mbar_arrive(BAR(MB_AUX));
  }
  {
    if (wg == 2) {
#pragma unroll
      for (int j = 0; j < 5; j++) { k[j][0] *= ksc; k[j][1] *= ksc; k[j][2] *= ksc; k[j][3] *= ksc; }
      nb_sync(NB_PREP, 256);
      {
        const uint32_t src = kp + 2048 + lane * 16;
        const uint4 v0 = lds128(src), v1 = lds128(src + 512), v2 = lds128(src + 1024);
        const uint32_t h[10] = {v0.x, v0.y, v0.z, v0.w, v1.x, v1.y, v1.z, v1.w, v2.x, v2.y};
#pragma unroll
        for (int j = 0; j < 10; j++) {
          const float2 f = __half22float2(*(const __half2*)&h[j]);
          k[j >> 1][2 * (j & 1)] = fmaf(f.x, uf(v2.w), k[j >> 1][2 * (j & 1)]);
          k[j >> 1][2 * (j & 1) + 1] = fmaf(f.y, uf(v2.w), k[j >> 1][2 * (j & 1) + 1]);
        }
        k2048 += uf(v2.z);
      }
#pragma unroll
      for (int o2 = 16; o2; o2 >>= 1) k2048 += __shfl_xor_sync(0xffffffffu, k2048, o2);
      if (lane == 0) k[0][0] += bf_lo(dsk);
      __syncwarp();
      TS(34);
      build_tables(tb, lane, k, k2048);
      TS(35);
      uint4* const g_y = P.xs + X_Y;
      conv_channel(sb + OFF_U + w * U_CH, tb, lane, g_y + (size_t)d * 256 + lane);
      nb_arrive(NB_BDONE, 288);
      nb_arrive(NB_Y, 160);
      TS(37);
      if (w == 0) TSDUMP(32);
      return;
    }
    if (wg == 1) {
      mbar_wait(BAR(MB_EMPTY + 4));
      mbar_spin(BAR(MB_EMPTY + 6));
    }
    TS(wg * 16 + 1);
  }

  float acc[2][48];
  {
    uint32_t fb = BAR(MB_FULL) + 64 * wg;
    uint32_t da = (uint32_t)mkdesc(sb + OFF_X, 16, 0, 0) + (wg ? 1024 : 3072), db = (uint32_t)mkdesc(sb + OFF_W, 4096, 0, 0);
    constexpr uint64_t ha = mkdesc(0, 0, 1024, 1), hb = mkdesc(0, 0, 512, 2);
    mbar_spin(fb);
    TS(wg * 16 + 2);
#pragma unroll 1
    for (int kb = 0; kb < 8; kb++) {
      WG_FENCE();
#pragma unroll
      for (int k = 0; k < 4; k++) {
        wgmma_ss_n96(acc[0], ha | (da + 2 * k), hb | (db + 64 * k), k ? 1 : kb);
        wgmma_ss_n96(acc[1], ha | (da + 2 * k + 512), hb | (db + 64 * k), k ? 1 : kb);
      }
      WG_COMMIT();
      if (kb < 7) mbar_spin(fb + 8);
      WG_WAIT(1);
      if (kb > 0) e_arrive(fb + 8 * (MB_EMPTY - MB_FULL - 1));
      fb += 8; db += 768;
      da = da == (uint32_t)mkdesc(sb + OFF_X + 65536, 16, 0, 0) ? da - 4096 : da + 1024;
    }
    WG_WAIT(0);
    e_arrive(fb + 8 * (MB_EMPTY - MB_FULL - 1));
    SPLIT();
  }
  TS(wg * 16 + 3);

  constexpr uint32_t stg0 = sb + OFF_STG0, stg1 = sb + OFF_X + 32768;
  uint4* const g_part = P.xs + X_PART;
  uint4* const g_o = P.xs + X_O;
  constexpr uint32_t kvs = stg0;
  auto pack8 = [](const float* a) { return make_uint4(pack_bf(a[0], a[1]), pack_bf(a[2], a[3]), pack_bf(a[4], a[5]), pack_bf(a[6], a[7])); };
  auto feat = [&](const uint4 (&af)[4], float (&p)[4][8]) {
    WG_FENCE();
#pragma unroll
    for (int u = 0; u < 4; u++) wgmma_rs_n16(p[u], af[u], qdesc(sb + OFF_PHI + (u & 1) * 512), 0);
    WG_COMMIT();
  };
  auto packp = [](const float (&p)[4][8], uint32_t (&pw)[16]) {
#pragma unroll
    for (int i = 0; i < 16; i++) pw[i] = pack_bf(p[i >> 2][(i & 1) + 2 * (i & 2)], p[i >> 2][(i & 1) + 2 * (i & 2) + 2]);
  };
  auto contract = [&](float (&kc)[20], uint32_t stg, int acc_in) {
    WG_FENCE();
#pragma unroll
    for (int s = 0; s < 8; s++) wgmma_ss_n40(kc, qdesc(stg + s * SLAB), qdesc(stg + s * SLAB + 2048), s ? 1 : acc_in);
    WG_COMMIT();
    WG_WAIT(0);
  };
  uint32_t eq[32];
  {
    uint4 af[4], aq[4], vp[4];
    float p[4][8];
#pragma unroll
    for (int u = 0; u < 4; u++) af[u] = pack8(acc[u >> 1] + 16 + 8 * (u & 1));
    feat(af, p);
#pragma unroll
    for (int u = 0; u < 4; u++) { aq[u] = pack8(acc[u >> 1] + 8 * (u & 1)); vp[u] = pack8(acc[u >> 1] + 32 + 8 * (u & 1)); }
    WG_WAIT(0);
    uint32_t pw[16], ek[32];
    packp(p, pw);
#pragma unroll
    for (int u = 0; u < 4; u++) dual_exp(pw + 4 * u, ek + 8 * u);
    TS(wg * 16 + 12);
    mbar_spin(wg ? BAR(MB_EMPTY + 15) : BAR(MB_AUX));
    float rs[8][4];
    WG_FENCE();
#pragma unroll
    for (int i = 0; i < 8; i++) wgmma_rs_n8(rs[i], make_uint4(ek[4 * i], ek[4 * i + 1], ek[4 * i + 2], ek[4 * i + 3]), qdesc(sb + OFF_ONE), 0);
    WG_COMMIT();
    feat(aq, p);
    const uint32_t sl = (wg ? stg1 : stg0) + w * SLAB + lane * 16;
#pragma unroll
    for (int i = 0; i < 4; i++) stsm4(sl + (i >> 1) * 4 * SLAB + 2048 + (i & 1) * 512, vp[i].x, vp[i].y, vp[i].z, vp[i].w);
    sts128(sl + (lane >> 4) * (4 * SLAB - 256) + 3072, 0x3F803F80u, 0x3F803F80u, 0x3F803F80u, 0x3F803F80u);
    WG_WAIT(1);
#pragma unroll
    for (int i = 0; i < 8; i++) {
      normalise(ek + 4 * i, rs[i]);
      stsm4(sl + (i >> 2) * 4 * SLAB + (i & 3) * 512, ek[4 * i], ek[4 * i + 1], ek[4 * i + 2], ek[4 * i + 3]);
    }
    asm volatile("fence.proxy.async.shared::cta;" ::: "memory");
    TS(wg * 16 + 13);
    if (wg) {
      nb_arrive(NB_ST0, 256);
      nb_arrive(NB_GATE, 256);
    } else {
      float kc[20];
      uint4* pp = g_part + (size_t)(hp * 8 + rt) * 144 + t;
      uint32_t* pz = (uint32_t*)(pp - t + 128) + w * 16 + c * 8 + g;
      asm volatile("" : "+l"(pp), "+l"(pz));
      nb_sync(NB_WG0, 128);
      contract(kc, stg0, 0);
      mbar_wait(BAR(MB_UFULL));
      TS(15);
      nb_sync(NB_ST0, 256);
      contract(kc, stg1, 1);
      TS(6);
      float kv[8];
#pragma unroll
      for (int i = 0; i < 8; i++) kv[i] = w & 2 ? kc[8 + i] : kc[i];
      st_x(pp, nz(pack_bf(kv[0], kv[1])), pack_bf(kv[2], kv[3]), pack_bf(kv[4], kv[5]), pack_bf(kv[6], kv[7]));
      if (c < 2) st_x32(pz, nz(fu(c ? kc[18] : kc[16])));
      TS(5);
    }
    SPLIT();
    WG_WAIT(0);
    packp(p, pw);
#pragma unroll
    for (int u = 0; u < 4; u++) dual_exp(pw + 4 * u, eq + 8 * u);
    SPLIT();
  }
  TS(wg * 16 + 4);
  if (wg == 1) {
    mbar_wait(BAR(MB_UFULL));
    const uint4* ps = g_part + (size_t)hp * 8 * 144 + t;
    const uint32_t* zs = (const uint32_t*)(g_part + (size_t)(hp * 8 + (lane >> 4) * 4) * 144 + 128) + w * 16 + (lane & 15);
    uint4 v[8];
    uint32_t zv[4];
#pragma unroll 1
    for (int it = 0; it < SPIN_MAX; it++) {
#pragma unroll
      for (int i = 0; i < 8; i++) v[i] = ld_x(ps + i * 144);
#pragma unroll
      for (int i = 0; i < 4; i++) zv[i] = ld_x32(zs + i * 576);
      uint32_t m = min(min(zv[0], zv[1]), min(zv[2], zv[3]));
#pragma unroll
      for (int i = 0; i < 8; i++) m = min(m, v[i].x);
      if (__all_sync(0xffffffffu, m != 0)) break;
    }
    float s[8];
    WG_FENCE();
#pragma unroll
    for (int r = 0; r < 8; r++) wgmma_rs_n16(s, v[r], qdesc(sb + OFF_EYE), r);
    WG_COMMIT();
    float zsum = (uf(zv[0]) + uf(zv[1])) + (uf(zv[2]) + uf(zv[3]));
    zsum += __shfl_xor_sync(0xffffffffu, zsum, 16);
    const uint32_t z1 = pack_bf(zsum, 1.f);
    if (lane < 16) sts128(kvs + w * 768 + 512 + lane * 16, z1, z1, z1, z1);
    WG_WAIT(0);
    stsm4(kvs + w * 768 + lane * 16, pack_bf(s[0], s[1]), pack_bf(s[2], s[3]), pack_bf(s[4], s[5]), pack_bf(s[6], s[7]));
    asm volatile("fence.proxy.async.shared::cta;" ::: "memory");
    TS(22);
  }
  nb_sync(NB_KV, 256);
  {
    float n[8][12];
    WG_FENCE();
#pragma unroll
    for (int i = 0; i < 8; i++) wgmma_rs_n24(n[i], make_uint4(eq[4 * i], eq[4 * i + 1], eq[4 * i + 2], eq[4 * i + 3]), qdesc(kvs + (i & 3) * 768), 0);
    WG_COMMIT();
    uint32_t* od = (uint32_t*)(g_o + (size_t)((rt * 4 + wg * 2) * 32 + hp * 2) * 128) + w * 64 + lane;
    WG_WAIT(0);
#pragma unroll
    for (int u = 0; u < 4; u++) {
      float(&np)[12] = n[2 * u];
      const float(&nm)[12] = n[2 * u + 1];
      const float q0 = np[9] * rcp(nm[9]), q1 = np[11] * rcp(nm[11]);
      const float r0 = rcp(fmaf(nm[8], q0, fmaf(np[9], 1e-6f, np[8]))), r1 = rcp(fmaf(nm[10], q1, fmaf(np[11], 1e-6f, np[10])));
#pragma unroll
      for (int i = 0; i < 8; i++) np[i] = fmaf(nm[i], (i & 2) ? q1 : q0, np[i]);
      uint32_t* o = od + (u >> 1) * 16384 + (u & 1) * 512;
      o[0] = pack_bf(np[0] * r0, np[1] * r0);
      o[32] = pack_bf(np[2] * r1, np[3] * r1);
      o[256] = pack_bf(np[4] * r0, np[5] * r0);
      o[288] = pack_bf(np[6] * r1, np[7] * r1);
      if (u == 1) SPLIT();
    }
  }
  TS(wg * 16 + 7);
  nb_arrive(NB_ODONE, 288);
  if (wg) {
    const uint4* src = P.xs + X_Y + (oct * 32 + c * 8) * 256 + (2 * w + (g >> 2)) * 32 + i8 * 4 + (g & 3);
    __nv_bfloat16* dst = P.out + (size_t)((2 * w + (g >> 2)) * 256 + i8 * 16 + (g & 3) * 2) * 1024 + 512 + oct * 32 + c * 8;
    nb_sync(NB_GATE + 1, 160);
    nb_sync(NB_Y + w, 160);
    uint4 v[8];
#pragma unroll 1
    for (int it = 0; it < SPIN_MAX; it++) {
      uint32_t m = 0xffffffffu;
#pragma unroll
      for (int i = 0; i < 8; i++) v[i] = ld_x(src + i * 256);
#pragma unroll
      for (int i = 0; i < 8; i++) m = min(m, v[i].x);
      if (__all_sync(0xffffffffu, m != 0)) break;
    }
#pragma unroll
    for (int i = 0; i < 8; i++) *(uint4*)(dst + (size_t)((i >> 2) * 128 + ((i >> 1) & 1) * 8 + (i & 1)) * 1024) = tr_row(v, i);
    TS(31);
    GT(63);
    if (w == 0) TSDUMP(16);
    return;
  }
  mbar_wait(BAR(MB_WO));
  nb_sync(NB_BDONE, 288);
  TS(8);
  mbar_spin(BAR(MB_O));
  TS(9);
  constexpr uint64_t ha = mkdesc(0, 0, 128, 0), hb = mkdesc(0, 0, 1024, 1);
  constexpr uint32_t da0 = (uint32_t)mkdesc(stg1, 1024, 0, 0), db0 = (uint32_t)mkdesc(sb + OFF_W, 8192, 0, 0);
  const uint32_t ot = ((sb + OFF_T + 1023) & ~1023u) + w * 4096;
  auto store_half = [&](const float* oc, int hf) {
#pragma unroll
    for (int i = 0; i < 8; i += 2)
      stsm4(ot + hf * 2048 + (lane & 15) * 128 + (((i + (lane >> 4)) ^ lane) & 7) * 16, pack_bf(oc[4 * i], oc[4 * i + 1]),
            pack_bf(oc[4 * i + 2], oc[4 * i + 3]), pack_bf(oc[4 * i + 4], oc[4 * i + 5]), pack_bf(oc[4 * i + 6], oc[4 * i + 7]));
    asm volatile("fence.proxy.async.shared::cta;" ::: "memory");
    __syncwarp();
    e_store2d(&mout, ot + hf * 2048, (hp & 3) * 128 + hf * 64, (rt * 4 + (hp >> 2)) * 64 + w * 16);
  };
  float oc[64];
#pragma unroll 1
  for (int j = 0; j < 8; j++) {
    const int kb = (j + 7) & 7;
    if ((j & 1) && j < 6) mbar_spin(BAR(MB_O + 1) + 4 * (j - 1));
    WG_FENCE();
#pragma unroll
    for (int k = 0; k < 4; k++) wgmma_ss_n128(oc, ha | (da0 + 512 * kb + 128 * k), hb | (db0 + 1024 * kb + 128 * k), k ? 1 : j);
    WG_COMMIT();
  }
  WG_WAIT(0);
  TS(10);
  store_half(oc, 0);
  store_half(oc + 32, 1);
  asm volatile(ELECT "cp.async.bulk.commit_group;\n@p cp.async.bulk.wait_group.read 0;\n}\n" ::: "memory");
  TS(wg * 16 + 11);
  GT(61 + wg);
  if (w == 0) TSDUMP(0);
  if (w == 1) TSDUMP(48);
}

typedef CUresult (*EncodeFn)(CUtensorMap*, CUtensorMapDataType, cuuint32_t, void*, const cuuint64_t*, const cuuint64_t*,
                             const cuuint32_t*, const cuuint32_t*, CUtensorMapInterleave, CUtensorMapSwizzle,
                             CUtensorMapL2promotion, CUtensorMapFloatOOBfill);

}

extern "C" void kernel_launch(void* const* d_in, const int* in_sizes, int n_in, void* d_out, int out_size) {
  (void)in_sizes; (void)n_in; (void)out_size;
  void* fn = nullptr;
  cudaDriverEntryPointQueryResult qr;
  cudaGetDriverEntryPoint("cuTensorMapEncodeTiled", &fn, cudaEnableDefault, &qr);
  EncodeFn enc = (EncodeFn)fn;
  CUtensorMap mx, mw, mo, mu, mout;
  const cuuint32_t es[5] = {1, 1, 1, 1, 1};
  {
    cuuint64_t dims[2] = {512, 2048}, st[1] = {1024};
    cuuint32_t box[2] = {64, 128};
    enc(&mx, CU_TENSOR_MAP_DATA_TYPE_BFLOAT16, 2, d_in[0], dims, st, box, es, CU_TENSOR_MAP_INTERLEAVE_NONE,
        CU_TENSOR_MAP_SWIZZLE_128B, CU_TENSOR_MAP_L2_PROMOTION_L2_128B, CU_TENSOR_MAP_FLOAT_OOB_FILL_NONE);
  }
  {
    cuuint64_t dims[3] = {512, 512, 3}, st[2] = {3072, 1024};
    cuuint32_t box[3] = {32, 64, 3};
    enc(&mw, CU_TENSOR_MAP_DATA_TYPE_BFLOAT16, 3, d_in[1], dims, st, box, es, CU_TENSOR_MAP_INTERLEAVE_NONE,
        CU_TENSOR_MAP_SWIZZLE_64B, CU_TENSOR_MAP_L2_PROMOTION_L2_128B, CU_TENSOR_MAP_FLOAT_OOB_FILL_NONE);
  }
  {
    cuuint64_t dims[3] = {64, 512, 8}, st[2] = {1024, 128};
    cuuint32_t box[3] = {64, 64, 2};
    enc(&mo, CU_TENSOR_MAP_DATA_TYPE_BFLOAT16, 3, d_in[3], dims, st, box, es, CU_TENSOR_MAP_INTERLEAVE_NONE,
        CU_TENSOR_MAP_SWIZZLE_128B, CU_TENSOR_MAP_L2_PROMOTION_L2_128B, CU_TENSOR_MAP_FLOAT_OOB_FILL_NONE);
  }
  {
    cuuint64_t dims[4] = {512, 4, 16, 32}, st[3] = {16384, 1024, 65536};
    cuuint32_t box[4] = {64, 4, 16, 2};
    enc(&mu, CU_TENSOR_MAP_DATA_TYPE_BFLOAT16, 4, d_in[4], dims, st, box, es, CU_TENSOR_MAP_INTERLEAVE_NONE,
        CU_TENSOR_MAP_SWIZZLE_128B, CU_TENSOR_MAP_L2_PROMOTION_L2_128B, CU_TENSOR_MAP_FLOAT_OOB_FILL_NONE);
  }
  {
    cuuint64_t dims[2] = {1024, 2048}, st[1] = {2048};
    cuuint32_t box[2] = {64, 16};
    enc(&mout, CU_TENSOR_MAP_DATA_TYPE_BFLOAT16, 2, d_out, dims, st, box, es, CU_TENSOR_MAP_INTERLEAVE_NONE,
        CU_TENSOR_MAP_SWIZZLE_128B, CU_TENSOR_MAP_L2_PROMOTION_NONE, CU_TENSOR_MAP_FLOAT_OOB_FILL_NONE);
  }
  Params P;
  P.x = (const __nv_bfloat16*)d_in[0];
  P.wphi = (const __nv_bfloat16*)d_in[2];
  P.wo = (const __nv_bfloat16*)d_in[3];
  P.logA = (const __nv_bfloat16*)d_in[5];
  P.Aim = (const __nv_bfloat16*)d_in[6];
  P.Cre = (const __nv_bfloat16*)d_in[7];
  P.Cim = (const __nv_bfloat16*)d_in[8];
  P.logdt = (const __nv_bfloat16*)d_in[9];
  P.Dskip = (const __nv_bfloat16*)d_in[10];
  P.out = (__nv_bfloat16*)d_out;
  cudaGetSymbolAddress((void**)&P.xs, g_x);
  P.ts = nullptr;
  cudaFuncSetAttribute(fused_kernel, cudaFuncAttributeMaxDynamicSharedMemorySize, SMEM_BYTES);
  fused_kernel<<<NCTA, NTHREADS, SMEM_BYTES>>>(P, mx, mw, mo, mu, mout);
}
```

```cpp
#include <cuda_runtime.h>
#include <cuda_bf16.h>
#include <cuda_fp16.h>
#include <cuda.h>
#include <stdint.h>

#define DBG_TS 0

namespace {

constexpr int NTHREADS = 512;
constexpr int NCTA = 128;
constexpr int OFF_W = 0;
constexpr int OFF_X = 98304;
constexpr int OFF_U = OFF_X + 65536;
constexpr int U_CH = 4416, U_ODD = 2240, U_PAD = 128;
constexpr int OFF_STG0 = OFF_U + 18432;
constexpr int SLAB = 3328;
constexpr int OFF_T = OFF_STG0 + 8 * SLAB;
constexpr int T_CH = 5216;
constexpr int T_D = 0;
constexpr int T_5 = 2144;
constexpr int T_3 = T_5 + 384;
constexpr int T_7 = T_5 + 1024;
constexpr int T_9 = T_7 + 320;
constexpr int T_KC = T_9 + 320;
constexpr int T_ST = T_5 - 1024;
constexpr int OFF_PHI = OFF_T + 4 * T_CH;
constexpr int OFF_EYE = OFF_PHI + 1024, OFF_ONE = OFF_EYE + 512;
constexpr int OFF_BAR = OFF_ONE + 256;
constexpr int SMEM_BYTES = OFF_BAR + 512 + 256 * DBG_TS;
constexpr uint32_t SB = 1024;
static_assert(T_KC + 2 * 656 <= T_CH, "table size");
static_assert(SMEM_BYTES <= 232448, "smem");
constexpr int MB_URAW = 0, MB_FULL = 1  , MB_WO = 17, MB_UFULL = 18, MB_O = 19  ,
              MB_EMPTY = 23  , MB_AUX = 39;
__host__ __device__ constexpr uint32_t BAR(int i) { return SB + OFF_BAR + 8 * i; }
constexpr int NB_WG0 = 1, NB_ODONE = 2, NB_ST0 = 3  , NB_KV = 5, NB_YZ = 6, NB_INIT = 7, NB_PREP = 8, NB_PROD = 9, NB_KREAD = 10, NB_BDONE = 11, NB_GATE = 12,
              NB_Y = 7  ;
#define X2_AT -1
#define GATE_B 2
#define POLL 0
#define GATE_AT 1
#define KG_AFTER 0
#define WARM_K 1
#define U_AT 2
#define ZERO_STEP 12
constexpr int SPIN_MAX = 1 << 16;

constexpr int X_CNT = 0;
constexpr int X_PART = 256;
constexpr int X_O = X_PART + 16 * 8 * 144;
constexpr int X_Y = X_O + 32 * 32 * 128;
constexpr int X_UT = X_Y + 512 * 8 * 32;
constexpr int X_SIZE = X_UT + 512 * (U_CH / 16);
__device__ __align__(128) uint4 g_x[X_SIZE];
extern __shared__ uint8_t smem_raw[];
#define TS(i) do {} while (0)
#define TS1(i) do {} while (0)
#define GT(i) do {} while (0)
#define TSDUMP(base) do {} while (0)

__device__ __forceinline__ uint32_t smem_u32(const void* p) { return (uint32_t)__cvta_generic_to_shared(p); }
__device__ __forceinline__ void mbar_arrive(uint32_t b) {
  asm volatile("mbarrier.arrive.shared::cta.b64 _, [%0];" ::"r"(b) : "memory");
}
__device__ __forceinline__ void mbar_wait(uint32_t b) {
  uint32_t done = 0;
#pragma unroll 1
  for (int i = 0; i < SPIN_MAX && !done; i++) {
    asm volatile("{\n.reg .pred p;\nmbarrier.try_wait.parity.shared::cta.b64 p, [%1], 0, 4000;\nselp.u32 %0, 1, 0, p;\n}\n"
                 : "=r"(done) : "r"(b) : "memory");
  }
}
__device__ __forceinline__ void mbar_spin(uint32_t b) {
  uint32_t done = 0;
#pragma unroll 1
  for (int i = 0; i < (SPIN_MAX << 4) && !done; i++) {
    asm volatile("{\n.reg .pred p;\nmbarrier.try_wait.parity.shared::cta.b64 p, [%1], 0;\nselp.u32 %0, 1, 0, p;\n}\n"
                 : "=r"(done) : "r"(b) : "memory");
  }
}
__device__ __forceinline__ void mbar_init(uint32_t b, int n) {
  asm volatile("mbarrier.init.shared::cta.b64 [%0], %1;" ::"r"(b), "r"(n) : "memory");
}
__device__ __forceinline__ void mbar_expect(uint32_t b, int bytes) {
  asm volatile("mbarrier.arrive.expect_tx.shared::cta.b64 _, [%0], %1;" ::"r"(b), "r"(bytes) : "memory");
}
__device__ __forceinline__ void nb_sync(int id, int n) { asm volatile("bar.sync %0, %1;" ::"r"(id), "r"(n) : "memory"); }
__device__ __forceinline__ void nb_arrive(int id, int n) { asm volatile("bar.arrive %0, %1;" ::"r"(id), "r"(n) : "memory"); }
#define ELECT "{\n.reg .pred p;\nelect.sync _|p, 0xffffffff;\n@p "
__device__ __forceinline__ void e_arrive(uint32_t b) {
  asm volatile(ELECT "mbarrier.arrive.shared::cta.b64 _, [%0];\n}\n" ::"r"(b) : "memory");
}
__device__ __forceinline__ void e_expect(uint32_t b, int bytes) {
  asm volatile(ELECT "mbarrier.arrive.expect_tx.shared::cta.b64 _, [%0], %1;\n}\n" ::"r"(b), "r"(bytes) : "memory");
}
__device__ __forceinline__ void e_tma2d(uint32_t dst, const CUtensorMap* m, uint32_t bar, int c0, int c1) {
  asm volatile(ELECT "cp.async.bulk.tensor.2d.shared::cluster.global.mbarrier::complete_tx::bytes [%0], [%1, {%3,%4}], [%2];\n}\n"
               ::"r"(dst), "l"(m), "r"(bar), "r"(c0), "r"(c1) : "memory");
}
__device__ __forceinline__ void e_tma3d(uint32_t dst, const CUtensorMap* m, uint32_t bar, int c0, int c1, int c2) {
  asm volatile(ELECT "cp.async.bulk.tensor.3d.shared::cluster.global.mbarrier::complete_tx::bytes [%0], [%1, {%3,%4,%5}], [%2];\n}\n"
               ::"r"(dst), "l"(m), "r"(bar), "r"(c0), "r"(c1), "r"(c2) : "memory");
}
__device__ __forceinline__ void e_tma4d(uint32_t dst, const CUtensorMap* m, uint32_t bar, int c0, int c3) {
  asm volatile(ELECT "cp.async.bulk.tensor.4d.shared::cluster.global.mbarrier::complete_tx::bytes [%0], [%1, {%3,%5,%5,%4}], [%2];\n}\n"
               ::"r"(dst), "l"(m), "r"(bar), "r"(c0), "r"(c3), "r"(0) : "memory");
}
__device__ __forceinline__ void e_bulk(uint32_t dst, const void* src, int bytes, uint32_t bar) {
  asm volatile(ELECT "cp.async.bulk.shared::cluster.global.mbarrier::complete_tx::bytes [%0], [%1], %2, [%3];\n}\n"
               ::"r"(dst), "l"(src), "r"(bytes), "r"(bar) : "memory");
}
__device__ __forceinline__ void e_prefetch(const void* p, int bytes) {
  asm volatile(ELECT "cp.async.bulk.prefetch.L2.global [%0], %1;\n}\n" ::"l"(p), "r"(bytes) : "memory");
}
__device__ __forceinline__ void e_store2d(const CUtensorMap* m, uint32_t src, int c0, int c1) {
  asm volatile(ELECT "cp.async.bulk.tensor.2d.global.shared::cta.bulk_group [%0, {%2,%3}], [%1];\n}\n"
               ::"l"(m), "r"(src), "r"(c0), "r"(c1) : "memory");
}
__host__ __device__ constexpr uint64_t mkdesc(uint32_t addr, uint32_t lbo, uint32_t sbo, int swz) {
  return (uint64_t)((addr & 0x3FFFF) >> 4) | ((uint64_t)(lbo >> 4) << 16) | ((uint64_t)(sbo >> 4) << 32) |
         ((uint64_t)swz << 62);
}
#define SPLIT() asm volatile("{\n.reg .pred p;\nsetp.eq.u32 p, %0, %1;\n@p exit;\n}\n" ::"r"(blockIdx.y), "n"(__LINE__) : "memory")
#define SPLITN(n) asm volatile("{\n.reg .pred p;\nsetp.eq.u32 p, %0, %1;\n@p exit;\n}\n" ::"r"(blockIdx.y), "r"(4096 + (n)) : "memory")
#define WG_FENCE() asm volatile("wgmma.fence.sync.aligned;" ::: "memory")
#define WG_COMMIT() asm volatile("wgmma.commit_group.sync.aligned;" ::: "memory")
#define WG_WAIT(n) asm volatile("wgmma.wait_group.sync.aligned " #n ";" ::: "memory")

__device__ __forceinline__ void mma(float& d0, float& d1, float& d2, float& d3, uint32_t a0, uint32_t a1, uint32_t a2,
                                    uint32_t a3, uint32_t b0, uint32_t b1) {
  asm volatile("mma.sync.aligned.m16n8k16.row.col.f32.bf16.bf16.f32 {%0,%1,%2,%3},{%4,%5,%6,%7},{%8,%9},{%0,%1,%2,%3};"
               : "+f"(d0), "+f"(d1), "+f"(d2), "+f"(d3)
               : "r"(a0), "r"(a1), "r"(a2), "r"(a3), "r"(b0), "r"(b1));
}
__device__ __forceinline__ void mmac(float (&d)[4], uint32_t a0, uint32_t a1, uint32_t a2, uint32_t a3, uint32_t b0,
                                     uint32_t b1, const float (&c)[4]) {
  asm volatile("mma.sync.aligned.m16n8k16.row.col.f32.bf16.bf16.f32 {%0,%1,%2,%3},{%4,%5,%6,%7},{%8,%9},{%10,%11,%12,%13};"
               : "=f"(d[0]), "=f"(d[1]), "=f"(d[2]), "=f"(d[3])
               : "r"(a0), "r"(a1), "r"(a2), "r"(a3), "r"(b0), "r"(b1), "f"(c[0]), "f"(c[1]), "f"(c[2]), "f"(c[3]));
}
__device__ __forceinline__ void mma_p(int p, float (&d)[4], uint32_t a0, uint32_t a1, uint32_t a2, uint32_t a3, uint32_t b0, uint32_t b1) {
  asm volatile("{\n.reg .pred q;\nsetp.ne.b32 q, %10, 0;\n"
               "@q mma.sync.aligned.m16n8k16.row.col.f32.bf16.bf16.f32 {%0,%1,%2,%3},{%4,%5,%6,%7},{%8,%9},{%0,%1,%2,%3};\n}\n"
               : "+f"(d[0]), "+f"(d[1]), "+f"(d[2]), "+f"(d[3])
               : "r"(a0), "r"(a1), "r"(a2), "r"(a3), "r"(b0), "r"(b1), "r"(p));
}
__device__ __forceinline__ void mmac_p(int p, float (&d)[4], uint32_t a0, uint32_t a1, uint32_t a2, uint32_t a3, uint32_t b0,
                                       uint32_t b1, const float (&c)[4]) {
  asm volatile("{\n.reg .pred q;\nsetp.ne.b32 q, %14, 0;\n"
               "@q mma.sync.aligned.m16n8k16.row.col.f32.bf16.bf16.f32 {%0,%1,%2,%3},{%4,%5,%6,%7},{%8,%9},{%10,%11,%12,%13};\n}\n"
               : "+f"(d[0]), "+f"(d[1]), "+f"(d[2]), "+f"(d[3])
               : "r"(a0), "r"(a1), "r"(a2), "r"(a3), "r"(b0), "r"(b1), "f"(c[0]), "f"(c[1]), "f"(c[2]), "f"(c[3]), "r"(p));
}
__device__ __forceinline__ void mma_h(float (&d)[4], const uint32_t (&a)[4], uint32_t b0, uint32_t b1) {
  asm volatile("mma.sync.aligned.m16n8k16.row.col.f32.f16.f16.f32 {%0,%1,%2,%3},{%4,%5,%6,%7},{%8,%9},{%0,%1,%2,%3};"
               : "+f"(d[0]), "+f"(d[1]), "+f"(d[2]), "+f"(d[3]) : "r"(a[0]), "r"(a[1]), "r"(a[2]), "r"(a[3]), "r"(b0), "r"(b1));
}
__device__ __forceinline__ void mma0(float& d0, float& d1, float& d2, float& d3, uint32_t a0, uint32_t a1, uint32_t a2,
                                     uint32_t a3, uint32_t b0, uint32_t b1) {
  asm volatile("mma.sync.aligned.m16n8k16.row.col.f32.bf16.bf16.f32 {%0,%1,%2,%3},{%4,%5,%6,%7},{%8,%9},{%10,%10,%10,%10};"
               : "=f"(d0), "=f"(d1), "=f"(d2), "=f"(d3)
               : "r"(a0), "r"(a1), "r"(a2), "r"(a3), "r"(b0), "r"(b1), "f"(0.f));
}
__device__ __forceinline__ uint32_t pack_bf(float lo, float hi) {
  uint32_t r;
  asm("cvt.rn.bf16x2.f32 %0, %1, %2;" : "=r"(r) : "f"(hi), "f"(lo));
  return r;
}
__device__ __forceinline__ float bf_lo(uint32_t w) { return __uint_as_float(w << 16); }
__device__ __forceinline__ float bf_hi(uint32_t w) { return __uint_as_float(w & 0xffff0000u); }
__device__ __forceinline__ float bf_round(float x) { return __bfloat162float(__float2bfloat16_rn(x)); }
__device__ __forceinline__ uint32_t bmax2(uint32_t a, uint32_t b) {
  uint32_t r; asm("max.bf16x2 %0, %1, %2;" : "=r"(r) : "r"(a), "r"(b)); return r;
}
__device__ __forceinline__ uint32_t bmin2(uint32_t a, uint32_t b) {
  uint32_t r; asm("min.bf16x2 %0, %1, %2;" : "=r"(r) : "r"(a), "r"(b)); return r;
}
__device__ __forceinline__ float ex2(float x) { float r; asm("ex2.approx.ftz.f32 %0, %1;" : "=f"(r) : "f"(x)); return r; }
__device__ __forceinline__ float rcp(float x) { float r; asm("rcp.approx.ftz.f32 %0, %1;" : "=f"(r) : "f"(x)); return r; }
__device__ __forceinline__ void ldsm4(uint32_t (&r)[4], uint32_t a) {
  asm volatile("ldmatrix.sync.aligned.m8n8.x4.shared.b16 {%0,%1,%2,%3}, [%4];"
               : "=r"(r[0]), "=r"(r[1]), "=r"(r[2]), "=r"(r[3]) : "r"(a) : "memory");
}
__device__ __forceinline__ void ldsm4t(uint32_t (&r)[4], uint32_t a) {
  asm volatile("ldmatrix.sync.aligned.m8n8.x4.trans.shared.b16 {%0,%1,%2,%3}, [%4];"
               : "=r"(r[0]), "=r"(r[1]), "=r"(r[2]), "=r"(r[3]) : "r"(a) : "memory");
}
__device__ __forceinline__ void stsm4(uint32_t a, uint32_t r0, uint32_t r1, uint32_t r2, uint32_t r3) {
  asm volatile("stmatrix.sync.aligned.m8n8.x4.shared.b16 [%0], {%1,%2,%3,%4};"
               ::"r"(a), "r"(r0), "r"(r1), "r"(r2), "r"(r3) : "memory");
}
__device__ __forceinline__ uint32_t lds32(uint32_t a) {
  uint32_t r; asm volatile("ld.shared.u32 %0, [%1];" : "=r"(r) : "r"(a) : "memory"); return r;
}
__device__ __forceinline__ uint32_t lds16(uint32_t a) {
  uint32_t r; asm volatile("{\n.reg .u16 h;\nld.shared.u16 h, [%1];\ncvt.u32.u16 %0, h;\n}\n" : "=r"(r) : "r"(a) : "memory"); return r;
}
__device__ __forceinline__ uint2 lds64(uint32_t a) {
  uint2 r; asm volatile("ld.shared.v2.u32 {%0,%1}, [%2];" : "=r"(r.x), "=r"(r.y) : "r"(a) : "memory"); return r;
}
__device__ __forceinline__ uint4 lds128(uint32_t a) {
  uint4 r;
  asm volatile("ld.shared.v4.u32 {%0,%1,%2,%3}, [%4];" : "=r"(r.x), "=r"(r.y), "=r"(r.z), "=r"(r.w) : "r"(a) : "memory");
  return r;
}
__device__ __forceinline__ void sts32(uint32_t a, uint32_t v) { asm volatile("st.shared.u32 [%0], %1;" ::"r"(a), "r"(v) : "memory"); }
__device__ __forceinline__ void sts16(uint32_t a, uint32_t v) {
  asm volatile("{\n.reg .u16 h;\ncvt.u16.u32 h, %1;\nst.shared.u16 [%0], h;\n}\n" ::"r"(a), "r"(v) : "memory");
}
__device__ __forceinline__ void sts64(uint32_t a, uint32_t x, uint32_t y) {
  asm volatile("st.shared.v2.u32 [%0], {%1,%2};" ::"r"(a), "r"(x), "r"(y) : "memory");
}
__device__ __forceinline__ void sts128(uint32_t a, uint32_t x, uint32_t y, uint32_t z, uint32_t w) {
  asm volatile("st.shared.v4.u32 [%0], {%1,%2,%3,%4};" ::"r"(a), "r"(x), "r"(y), "r"(z), "r"(w) : "memory");
}
__device__ __forceinline__ uint4 ld_x(const uint4* p) {
  uint4 r;
  asm volatile("{\n.reg .b128 t;\nld.relaxed.gpu.global.b128 t, [%4];\nmov.b128 {%0,%1,%2,%3}, t;\n}\n"
               : "=r"(r.x), "=r"(r.y), "=r"(r.z), "=r"(r.w) : "l"(p) : "memory");
  return r;
}
__device__ __forceinline__ uint32_t ld_x32(const uint32_t* p) {
  uint32_t r; asm volatile("ld.relaxed.gpu.global.u32 %0, [%1];" : "=r"(r) : "l"(p) : "memory"); return r;
}
__device__ __forceinline__ void st_x(uint4* p, uint32_t x, uint32_t y, uint32_t z, uint32_t w) {
  asm volatile("{\n.reg .b128 t;\nmov.b128 t, {%1,%2,%3,%4};\nst.relaxed.gpu.global.b128 [%0], t;\n}\n"
               ::"l"(p), "r"(x), "r"(y), "r"(z), "r"(w) : "memory");
}
__device__ __forceinline__ void st_x_p(int p, uint4* a, uint32_t x, uint32_t y, uint32_t z, uint32_t w) {
  asm volatile("{\n.reg .b128 t;\n.reg .pred q;\nsetp.ne.b32 q, %5, 0;\nmov.b128 t, {%1,%2,%3,%4};\n@q st.relaxed.gpu.global.b128 [%0], t;\n}\n"
               ::"l"(a), "r"(x), "r"(y), "r"(z), "r"(w), "r"(p) : "memory");
}
__device__ __forceinline__ void sts64_p(int p, uint32_t a, uint32_t x, uint32_t y) {
  asm volatile("{\n.reg .pred q;\nsetp.ne.b32 q, %3, 0;\n@q st.shared.v2.u32 [%0], {%1,%2};\n}\n" ::"r"(a), "r"(x), "r"(y), "r"(p) : "memory");
}
__device__ __forceinline__ void st_x32(uint32_t* p, uint32_t x) {
  asm volatile("st.relaxed.gpu.global.u32 [%0], %1;" ::"l"(p), "r"(x) : "memory");
}
__device__ __forceinline__ uint32_t nz(uint32_t w) { return max(w, 1u); }
__device__ __forceinline__ uint32_t fu(float x) { return __float_as_uint(x); }
__device__ __forceinline__ float uf(uint32_t x) { return __uint_as_float(x); }

__device__ __forceinline__ void wgmma_ss_n96(float (&d)[48], uint64_t da, uint64_t db, int sc) {
  asm volatile("{\n.reg .pred p;\nsetp.ne.b32 p, %50, 0;\n"
      "wgmma.mma_async.sync.aligned.m64n96k16.f32.bf16.bf16 "
      "{%0,%1,%2,%3,%4,%5,%6,%7,%8,%9,%10,%11,%12,%13,%14,%15,%16,%17,%18,%19,%20,%21,%22,%23,%24,%25,%26,%27,%28,%29,%30,%31,%32,%33,%34,%35,%36,%37,%38,%39,%40,%41,%42,%43,%44,%45,%46,%47}, "
      "%48, %49, p, 1, 1, 0, 1;\n}\n"
      : "+f"(d[0]), "+f"(d[1]), "+f"(d[2]), "+f"(d[3]), "+f"(d[4]), "+f"(d[5]), "+f"(d[6]), "+f"(d[7]),
        "+f"(d[8]), "+f"(d[9]), "+f"(d[10]), "+f"(d[11]), "+f"(d[12]), "+f"(d[13]), "+f"(d[14]), "+f"(d[15]),
        "+f"(d[16]), "+f"(d[17]), "+f"(d[18]), "+f"(d[19]), "+f"(d[20]), "+f"(d[21]), "+f"(d[22]), "+f"(d[23]),
        "+f"(d[24]), "+f"(d[25]), "+f"(d[26]), "+f"(d[27]), "+f"(d[28]), "+f"(d[29]), "+f"(d[30]), "+f"(d[31]),
        "+f"(d[32]), "+f"(d[33]), "+f"(d[34]), "+f"(d[35]), "+f"(d[36]), "+f"(d[37]), "+f"(d[38]), "+f"(d[39]),
        "+f"(d[40]), "+f"(d[41]), "+f"(d[42]), "+f"(d[43]), "+f"(d[44]), "+f"(d[45]), "+f"(d[46]), "+f"(d[47])
      : "l"(da), "l"(db), "r"(sc));
}

__device__ __forceinline__ void wgmma_ss_n128(float (&d)[64], uint64_t da, uint64_t db, int sc) {
  asm volatile("{\n.reg .pred p;\nsetp.ne.b32 p, %66, 0;\n"
      "wgmma.mma_async.sync.aligned.m64n128k16.f32.bf16.bf16 "
      "{%0,%1,%2,%3,%4,%5,%6,%7,%8,%9,%10,%11,%12,%13,%14,%15,%16,%17,%18,%19,%20,%21,%22,%23,%24,%25,%26,%27,%28,%29,%30,%31,%32,%33,%34,%35,%36,%37,%38,%39,%40,%41,%42,%43,%44,%45,%46,%47,%48,%49,%50,%51,%52,%53,%54,%55,%56,%57,%58,%59,%60,%61,%62,%63}, "
      "%64, %65, p, 1, 1, 0, 1;\n}\n"
      : "+f"(d[0]), "+f"(d[1]), "+f"(d[2]), "+f"(d[3]), "+f"(d[4]), "+f"(d[5]), "+f"(d[6]), "+f"(d[7]),
        "+f"(d[8]), "+f"(d[9]), "+f"(d[10]), "+f"(d[11]), "+f"(d[12]), "+f"(d[13]), "+f"(d[14]), "+f"(d[15]),
        "+f"(d[16]), "+f"(d[17]), "+f"(d[18]), "+f"(d[19]), "+f"(d[20]), "+f"(d[21]), "+f"(d[22]), "+f"(d[23]),
        "+f"(d[24]), "+f"(d[25]), "+f"(d[26]), "+f"(d[27]), "+f"(d[28]), "+f"(d[29]), "+f"(d[30]), "+f"(d[31]),
        "+f"(d[32]), "+f"(d[33]), "+f"(d[34]), "+f"(d[35]), "+f"(d[36]), "+f"(d[37]), "+f"(d[38]), "+f"(d[39]),
        "+f"(d[40]), "+f"(d[41]), "+f"(d[42]), "+f"(d[43]), "+f"(d[44]), "+f"(d[45]), "+f"(d[46]), "+f"(d[47]),
        "+f"(d[48]), "+f"(d[49]), "+f"(d[50]), "+f"(d[51]), "+f"(d[52]), "+f"(d[53]), "+f"(d[54]), "+f"(d[55]),
        "+f"(d[56]), "+f"(d[57]), "+f"(d[58]), "+f"(d[59]), "+f"(d[60]), "+f"(d[61]), "+f"(d[62]), "+f"(d[63])
      : "l"(da), "l"(db), "r"(sc));
}

__device__ __forceinline__ void wgmma_ss_n40(float (&d)[20], uint64_t da, uint64_t db, int sc) {
  asm volatile("{\n.reg .pred p;\nsetp.ne.b32 p, %22, 0;\n"
      "wgmma.mma_async.sync.aligned.m64n40k16.f32.bf16.bf16 "
      "{%0,%1,%2,%3,%4,%5,%6,%7,%8,%9,%10,%11,%12,%13,%14,%15,%16,%17,%18,%19}, "
      "%20, %21, p, 1, 1, 1, 1;\n}\n"
      : "+f"(d[0]), "+f"(d[1]), "+f"(d[2]), "+f"(d[3]), "+f"(d[4]), "+f"(d[5]), "+f"(d[6]), "+f"(d[7]),
        "+f"(d[8]), "+f"(d[9]), "+f"(d[10]), "+f"(d[11]), "+f"(d[12]), "+f"(d[13]), "+f"(d[14]), "+f"(d[15]),
        "+f"(d[16]), "+f"(d[17]), "+f"(d[18]), "+f"(d[19])
      : "l"(da), "l"(db), "r"(sc));
}

__device__ __forceinline__ void wgmma_rs_n8(float (&d)[4], const uint4& a, uint64_t db, int sc) {
  asm volatile("{\n.reg .pred p;\nsetp.ne.b32 p, %9, 0;\n"
      "wgmma.mma_async.sync.aligned.m64n8k16.f32.bf16.bf16 "
      "{%0,%1,%2,%3}, "
      "{%4,%5,%6,%7}, %8, p, 1, 1, 1;\n}\n"
      : "+f"(d[0]), "+f"(d[1]), "+f"(d[2]), "+f"(d[3])
      : "r"(a.x), "r"(a.y), "r"(a.z), "r"(a.w), "l"(db), "r"(sc));
}

__device__ __forceinline__ void wgmma_rs_n16(float (&d)[8], const uint4& a, uint64_t db, int sc) {
  asm volatile("{\n.reg .pred p;\nsetp.ne.b32 p, %13, 0;\n"
      "wgmma.mma_async.sync.aligned.m64n16k16.f32.bf16.bf16 "
      "{%0,%1,%2,%3,%4,%5,%6,%7}, "
      "{%8,%9,%10,%11}, %12, p, 1, 1, 1;\n}\n"
      : "+f"(d[0]), "+f"(d[1]), "+f"(d[2]), "+f"(d[3]), "+f"(d[4]), "+f"(d[5]), "+f"(d[6]), "+f"(d[7])
      : "r"(a.x), "r"(a.y), "r"(a.z), "r"(a.w), "l"(db), "r"(sc));
}

__device__ __forceinline__ void wgmma_rs_n24(float (&d)[12], const uint4& a, uint64_t db, int sc) {
  asm volatile("{\n.reg .pred p;\nsetp.ne.b32 p, %17, 0;\n"
      "wgmma.mma_async.sync.aligned.m64n24k16.f32.bf16.bf16 "
      "{%0,%1,%2,%3,%4,%5,%6,%7,%8,%9,%10,%11}, "
      "{%12,%13,%14,%15}, %16, p, 1, 1, 1;\n}\n"
      : "+f"(d[0]), "+f"(d[1]), "+f"(d[2]), "+f"(d[3]), "+f"(d[4]), "+f"(d[5]), "+f"(d[6]), "+f"(d[7]),
        "+f"(d[8]), "+f"(d[9]), "+f"(d[10]), "+f"(d[11])
      : "r"(a.x), "r"(a.y), "r"(a.z), "r"(a.w), "l"(db), "r"(sc));
}

struct Params {
  const __nv_bfloat16 *logA, *Aim, *Cre, *Cim, *logdt, *Dskip, *x, *wphi, *wo;
  __nv_bfloat16* out;
  uint4* xs;
  long long* ts;
};

__device__ __forceinline__ uint4 tr_row(const uint4 (&v)[8], int i) {
  uint32_t o[4];
#pragma unroll
  for (int m = 0; m < 4; m++) {
    const uint4 &ra = v[2 * m], &rb = v[2 * m + 1];
    const int k = i >> 1;
    const uint32_t xa = k == 0 ? ra.x : k == 1 ? ra.y : k == 2 ? ra.z : ra.w;
    const uint32_t xb = k == 0 ? rb.x : k == 1 ? rb.y : k == 2 ? rb.z : rb.w;
    o[m] = __byte_perm(xa, xb, (i & 1) ? 0x7632 : 0x5410);
  }
  return make_uint4(o[0], o[1], o[2], o[3]);
}

struct cpx { float r, i; };
__device__ __forceinline__ cpx csq(cpx a) { return {a.r * a.r - a.i * a.i, 2.f * (a.r * a.i)}; }
__device__ __forceinline__ cpx polar(float e, float t) {
  const float m = ex2(e);
  return {m * __cosf(t), m * __sinf(t)};
}

struct KgenRaw { uint32_t la, ai, cr, ci, ldt; };
__device__ __forceinline__ KgenRaw kgen_load(const Params& P, int d, int unit, int lane, int on) {
  const int o = d * 64 + unit * 32 + lane;
  KgenRaw r = {0, 0, 0, 0, 0};
  asm volatile("{\n.reg .pred p;\nsetp.ne.b32 p, %10, 0;\n@p ld.global.nc.u32 %0, [%5];\n@p ld.global.nc.u32 %1, [%6];\n"
               "@p ld.global.nc.u32 %2, [%7];\n@p ld.global.nc.u32 %3, [%8];\n@p ld.global.nc.u16 %4, [%9];\n}\n"
               : "+r"(r.la), "+r"(r.ai), "+r"(r.cr), "+r"(r.ci), "+r"(r.ldt)
               : "l"((const uint32_t*)P.logA + o), "l"((const uint32_t*)P.Aim + o), "l"((const uint32_t*)P.Cre + o),
                 "l"((const uint32_t*)P.Cim + o), "l"(P.logdt + d), "r"(on));
  return r;
}
struct hc { __half2 r, i; };
struct cpx2 { cpx a, b; };
__device__ __forceinline__ cpx2 csq2(const cpx2& v) { return {csq(v.a), csq(v.b)}; }
__device__ __forceinline__ hc toh(const cpx2& v) { return {__floats2half2_rn(v.a.r, v.b.r), __floats2half2_rn(v.a.i, v.b.i)}; }
__device__ __forceinline__ hc hmul(const hc& z, const hc& w) {
  return {__hfma2(z.r, w.r, __hneg2(__hmul2(z.i, w.i))), __hfma2(z.r, w.i, __hmul2(z.i, w.r))};
}
__device__ __forceinline__ hc hmulc(const hc& z, const hc& w) {
  return {__hfma2(z.r, w.r, __hmul2(z.i, w.i)), __hfma2(z.i, w.r, __hneg2(__hmul2(z.r, w.i)))};
}
__device__ __forceinline__ uint32_t hu(__half2 v) { return *(const uint32_t*)&v; }
__device__ __forceinline__ __half2 uh(uint32_t v) { return *(const __half2*)&v; }

struct KgenAddr { uint32_t sa, lb, lm[4]; };
__device__ __forceinline__ KgenAddr kgen_addr(int lane, uint32_t buf) {
  KgenAddr a;
  a.sa = buf + (lane & 7) * 128 + ((((lane >> 3) ^ lane) & 7) << 4);
  const int q = lane >> 4;
  const uint32_t b = buf + ((lane >> 3) & 1) * 1024 + q * 128;
  a.lb = b + (((lane ^ q) & 7) << 4);
  a.lm[0] = b + (q << 4);
  a.lm[1] = b + ((1 ^ q) << 4);
  a.lm[2] = b + (((2 + (lane & 1)) ^ q) << 4);
  a.lm[3] = b + (((4 + (lane & 3)) ^ q) << 4);
  asm volatile("" : "+r"(a.sa), "+r"(a.lb), "+r"(a.lm[0]), "+r"(a.lm[1]), "+r"(a.lm[2]), "+r"(a.lm[3]));
  return a;
}
__device__ __forceinline__ void kgen_unit(const KgenRaw& r, const KgenAddr& ad, uint32_t zero, float (&k)[5][4], float& k2048, float& sc) {
  const float dt = bf_round(expf(bf_lo(r.ldt)));
  const uint32_t ar = pack_bf(ex2(bf_lo(r.la) * 1.4426950408889634f), ex2(bf_hi(r.la) * 1.4426950408889634f));
  const float ca = dt * -1.4426950408889634f, a0 = bf_lo(ar) * ca, a1 = bf_hi(ar) * ca;
  const float f0 = bf_lo(r.ai) * dt, f1 = bf_hi(r.ai) * dt;
  const float r0 = f0 * 20.21267777267071f, r1 = f1 * 20.21267777267071f;
  const uint32_t cm = __vmaxu2(r.cr & 0x7fff7fffu, r.ci & 0x7fff7fffu);
  const uint32_t ex = min(max(__reduce_max_sync(0xffffffffu, max(cm >> 16, cm & 0xffffu)) >> 7, 1u), 253u);
  const float cs = uf((254u - ex) << 23);
  sc = 2.f * dt * uf(ex << 23);
  const cpx2 C = {{bf_lo(r.cr) * cs, bf_lo(r.ci) * -cs}, {bf_hi(r.cr) * cs, bf_hi(r.ci) * -cs}};
  auto put = [&](const hc (&v)[8]) {
    stsm4(ad.sa, hu(v[0].r), hu(v[1].r), hu(v[2].r), hu(v[3].r));
    stsm4(ad.sa + 1024, hu(v[0].i), hu(v[1].i), hu(v[2].i), hu(v[3].i));
    stsm4(ad.sa ^ 64, hu(v[4].r), hu(v[5].r), hu(v[6].r), hu(v[7].r));
    stsm4((ad.sa ^ 64) + 1024, hu(v[4].i), hu(v[5].i), hu(v[6].i), hu(v[7].i));
    __syncwarp();
  };
  auto get = [&](uint32_t (&o)[4][4], uint32_t a) {
#pragma unroll
    for (int i = 0; i < 4; i++) ldsm4(o[i], (a ^ (i << 5)) + i * 256);
  };
  auto at = [](const uint32_t (&o)[4][4], int s) { return hc{uh(o[s >> 1][2 * (s & 1)]), uh(o[s >> 1][2 * (s & 1) + 1])}; };
  uint32_t A[8][4];
  auto tile = [&](int j, const uint32_t (&B)[4][4]) {
    k[j][0] = k[j][1] = k[j][2] = k[j][3] = 0.f;
#pragma unroll
    for (int s = 0; s < 8; s++) mma_h(k[j], A[s], B[s >> 1][2 * (s & 1)], B[s >> 1][2 * (s & 1) + 1]);
  };
  auto after = [&](cpx2 v, uint32_t dep) { v.a.r = uf(fu(v.a.r) ^ (dep & zero)); v.b.r = uf(fu(v.b.r) ^ (dep & zero)); return v; };
  const cpx2 w1 = {polar(a0, f0), polar(a1, f1)};
  const cpx2 w127 = {polar(a0 * 127.f, (r0 - rintf(r0)) * 6.283185307179586f), polar(a1 * 127.f, (r1 - rintf(r1)) * 6.283185307179586f)};
  const cpx2 w2 = csq2(w1), w4 = csq2(w2);
  uint32_t T0[4][4], X[4][4], M[3][4][4];
  {
    hc t[8];
    t[0] = {uh(0x3C003C00u), uh(0u)}; t[1] = toh(w1); t[2] = toh(w2); t[4] = toh(w4);
    t[3] = hmul(t[1], t[2]); t[5] = hmul(t[1], t[4]); t[6] = hmul(t[2], t[4]); t[7] = hmul(t[3], t[4]);
    put(t); get(T0, ad.lb);
  }
  const cpx2 w8 = csq2(w4), w16 = csq2(w8), w32 = csq2(w16), w64 = csq2(w32);
  {
    const hc m8 = toh(w8), m16 = toh(w16), m32 = toh(w32);
    hc a[8];
    a[0] = toh(C); a[1] = hmulc(a[0], m8);
    a[2] = hmulc(a[0], m16); a[3] = hmulc(a[1], m16);
#pragma unroll
    for (int i = 0; i < 4; i++) a[4 + i] = hmulc(a[i], m32);
    put(a); get(X, ad.lb);
  }
  const cpx2 w127b = KG_AFTER ? after(w127, T0[0][0]) : w127;
  const cpx2 w128 = {{w127b.a.r * w1.a.r - w127b.a.i * w1.a.i, w127b.a.r * w1.a.i + w127b.a.i * w1.a.r},
                     {w127b.b.r * w1.b.r - w127b.b.i * w1.b.i, w127b.b.r * w1.b.i + w127b.b.i * w1.b.r}};
  const cpx2 w256 = csq2(w128), w512 = csq2(w256);
  const hc m128 = toh(w128), m256 = toh(w256), m512 = toh(w512);
  {
    const hc m254 = toh(csq2(w127b)), m127 = toh(w127b);
    hc m[8];
    m[0] = toh(w64); m[1] = m128; m[2] = m256; m[3] = hmul(m127, m256);
    m[4] = m512; m[5] = hmul(m127, m512); m[6] = hmul(m[4], m254); m[7] = hmul(m[5], m254);
    put(m);
    get(M[0], ad.lm[0]);
#pragma unroll
    for (int s = 0; s < 8; s++) {
      const hc z = at(X, s), y = hmulc(z, at(M[0], s));
      A[s][0] = hu(z.r) + zero; A[s][1] = hu(y.r); A[s][2] = hu(z.i) + zero; A[s][3] = hu(y.i);
    }
#pragma unroll
    for (int i = 0; i < 3; i++) get(M[i], ad.lm[i + 1]);
  }
  tile(0, T0);
  const cpx2 w1024 = csq2(KG_AFTER ? after(w512, X[0][0]) : w512), we = csq2(w1024);
  {
    hc t[8];
    t[0] = toh(w1024); t[1] = hmul(t[0], m128);
    t[2] = hmul(t[0], m256); t[3] = hmul(t[1], m256);
#pragma unroll
    for (int i = 0; i < 4; i++) t[4 + i] = hmul(t[i], m512);
    put(t); get(X, ad.lb);
  }
  k2048 = (C.a.r * we.a.r + C.a.i * we.a.i + C.b.r * we.b.r + C.b.i * we.b.i) * sc;
#pragma unroll
  for (int j = 1; j < 5; j++) k[j][0] = k[j][1] = k[j][2] = k[j][3] = 0.f;
#pragma unroll
  for (int s = 0; s < 8; s++) {
#pragma unroll
    for (int j = 0; j < 3; j++) {
      const hc y = hmul(at(T0, s), at(M[j], s));
      mma_h(k[1 + j], A[s], hu(y.r), hu(y.i));
    }
    mma_h(k[4], A[s], X[s >> 1][2 * (s & 1)], X[s >> 1][2 * (s & 1) + 1]);
  }
}

__device__ __forceinline__ void build_tables(uint32_t tb, int lane, float (&k)[5][4], float k2048) {
  const int g = lane >> 2, c = lane & 3;
  const uint32_t kc = tb + T_KC + 16;
  {
    const uint32_t a0 = kc + 16 * g + 4 * c, a2 = kc + 2 * (256 + 4 * g + c);
    const uint32_t a3 = kc + 2 * (384 + 2 * g + 64 * (c & 1) + (c >> 1)), a4 = kc + 2 * (512 + g + 32 * c);
#pragma unroll
    for (int r = 0; r < 2; r++) {
      sts32(a0 + 128 * r, pack_bf(k[0][2 * r], k[0][2 * r + 1]));
      sts32(a0 + 128 * r + 256, pack_bf(k[1][2 * r], k[1][2 * r + 1]));
      const uint32_t w2 = pack_bf(k[2][2 * r], k[2][2 * r + 1]);
      const uint32_t w3 = pack_bf(k[3][2 * r], k[3][2 * r + 1]);
      const uint32_t w4 = pack_bf(k[4][2 * r], k[4][2 * r + 1]);
      sts16(a2 + 64 * r, w2); sts16(a2 + 64 * r + 128, w2 >> 16);
      sts16(a3 + 32 * r, w3); sts16(a3 + 32 * r + 64, w3 >> 16);
      sts16(a4 + 16 * r, w4); sts16(a4 + 16 * r + 32, w4 >> 16);
    }
  }
  if (lane == 0) { sts16(kc + 2 * 640, pack_bf(k2048, 0.f)); sts32(kc - 4, 0); }
  __syncwarp();
  const uint32_t td = tb + T_D + 32;
#pragma unroll
  for (int hf = 0; hf < 2; hf++) {
    const uint2 v = lds64(kc + 256 * hf + 8 * lane);
    const uint32_t pv = lds32(kc + 256 * hf + 8 * lane - 4);
    sts128(td + 512 * hf + 16 * lane, __byte_perm(v.x, pv, 0x7610), __byte_perm(v.x, v.x, 0x1032), __byte_perm(v.y, v.x, 0x7610),
           __byte_perm(v.y, v.y, 0x1032));
  }
#pragma unroll
  for (int hf = 0; hf < 2; hf++) {
    const uint32_t v = lds32(kc + 512 + 128 * hf + 4 * lane), nx = lds32(kc + 516 + 128 * hf + 4 * lane);
    uint32_t w0 = __byte_perm(v, v, 0x1010);
    const uint32_t w1 = w0;
    if (hf == 0) { const uint32_t pv = lds32(kc + 508); if (lane == 0) w0 = __byte_perm(v, pv, 0x7610); }
    sts128(td + 1024 + 512 * hf + 16 * lane, w0, w1, __byte_perm(v, v, 0x1032), __byte_perm(nx, v, 0x7610));
  }
  {
    const uint32_t kk = lds16(kc + 2 * 384);
    const uint32_t w = lane < 3 ? (kk | (kk << 16)) : (lane == 3 ? (kk << 16) : 0u);
    if (lane < 24) sts32(td + 4 * (lane < 16 ? 512 + lane : lane - 24), w);
    const uint32_t lo_ = lds16(kc + 2 * 511), le_ = lds16(kc + 2 * 512);
    const uint32_t ja = tb + T_5 + (lane < 16 ? 4 * lane : 256 + 4 * lane);
    sts32(ja, lane == 16 ? (le_ << 16) : 0u);
    sts32(ja + 384, lane == 16 ? (lo_ << 16) : 0u);
    sts32(tb + (lane < 16 ? T_7 : T_9 - 64) + 4 * lane, 0u);
  }
#pragma unroll
  for (int s = 0; s < 2; s++) {
    const uint32_t b = kc + 2 * (s ? 512 : 384) + 8 * lane;
    const uint2 v = lds64(b);
    uint32_t em = lds16(b - 2), e0 = v.x;
    const uint32_t e4 = lds16(b + 8);
    if (lane == 0) { em = 0; e0 = 0; }
    sts64(tb + (s ? T_7 : T_3) + 64 + 8 * lane, __byte_perm(v.x, em, 0x5432), __byte_perm(v.y, v.x, 0x7632));
    sts64(tb + (s ? T_9 : T_5) + 64 + 8 * lane, __byte_perm(v.y, e0, 0x5410), __byte_perm(e4, v.y, 0x5410));
  }
  __syncwarp();
}

__device__ __forceinline__ uint32_t box2w(int lo, int n, int o) {
  return ((unsigned)(o - lo) < (unsigned)n ? 0x3F80u : 0u) | ((unsigned)(o + 1 - lo) < (unsigned)n ? 0x3F800000u : 0u);
}

__device__ __forceinline__ void conv_channel(uint32_t ub, uint32_t tb, int lane, uint4* ydst) {
  const int g = lane >> 2, c = lane & 3, x = g - 2 * c;
  const int mi = lane >> 3;
  const uint32_t qa = ub + U_PAD + 16 * (lane & 7) + ((mi == 0 || mi == 3) ? U_ODD : 0) - (mi == 0 ? 16 : 0);
  const uint32_t hb = ub + U_PAD + (mi & 1) * U_ODD + 16 * ((lane >> 4) + (lane & 7)) - 16;
  const uint32_t kv = lds16(tb + T_KC + 16 + 2 * 512);
  const int oh = c < 2 ? 8 + 2 * c : 2 * c - 8, og = c < 3 ? 2 * c : -10;
  uint32_t bx[4] = {box2w(g - 4, 9, 2 * c), box2w(g - 3, 7, 2 * c), box2w(g - 4, 9, oh), box2w(g - 3, 7, oh)};
  uint32_t by[4] = {box2w(g - 10, 5, 2 * c - 8), box2w(g - 5, 3, 2 * c - 8), box2w(g - 10, 5, og), box2w(g - 5, 3, og)};
  uint32_t lb0 = ((unsigned)(x + 5) < 2u ? kv : 0u) | ((unsigned)(x + 4) < 2u ? kv << 16 : 0u);
  uint32_t lb1 = ((unsigned)(x - 3) < 2u ? kv : 0u) | ((unsigned)(x - 4) < 2u ? kv << 16 : 0u);
  const int q0 = g - 1, q1 = c < 3 ? g : g - 2;
  uint32_t y0a = ub + U_PAD + (q0 & 1) * U_ODD + 16 * (q0 >> 1) + 4 * c;
  uint32_t y1a = ub + U_PAD + (q1 & 1) * U_ODD + 16 * (q1 >> 1) + 4 * c;
#pragma unroll
  for (int i = 0; i < 4; i++) asm volatile("" : "+r"(bx[i]), "+r"(by[i]));
  asm volatile("" : "+r"(lb0), "+r"(lb1), "+r"(y0a), "+r"(y1a));
  mbar_wait(BAR(MB_UFULL));
  mbar_spin(BAR(MB_EMPTY + 15));
  TS(36);
  float acc[16][4];
  {
    uint32_t z09[8], z07[8], zm9[8], zm7[8];
#pragma unroll
    for (int i = 0; i < 8; i++) {
      uint32_t h[4];
      ldsm4(h, hb + 128 * i);
      float y0, y1, y2, y3, w0, w1, w2, w3;
      mma0(y0, y1, y2, y3, bx[0], bx[1], bx[2], bx[3], h[2], c < 2 ? h[3] : h[1]);
      mma0(w0, w1, w2, w3, bx[0], bx[1], bx[2], bx[3], h[1], c < 2 ? h[2] : h[0]);
      z09[i] = pack_bf(y0, y1); z07[i] = pack_bf(y2, y3);
      zm9[i] = pack_bf(w0, w1); zm7[i] = pack_bf(w2, w3);
    }
  uint32_t f3[3][4][4];
  {
    const uint32_t fa = tb + T_7 + 4 * (16 + x);
#pragma unroll
    for (int tt = 0; tt < 3; tt++)
#pragma unroll
      for (int D = 0; D < 4; D++) {
        const uint32_t a = fa + (tt == 0 ? 316 : (tt == 1 ? 320 : 0)) + 64 * D;
        f3[tt][D][0] = lds32(a); f3[tt][D][1] = lds32(a + 32); f3[tt][D][2] = lds32(a - 32); f3[tt][D][3] = lds32(a);
      }
  }
    SPLIT();
    nb_sync(NB_GATE, 256);
    SPLIT();
    float a[4][2][4];
#pragma unroll
    for (int kap = 0; kap < 4; kap++)
#pragma unroll
      for (int sg = 0; sg < 2; sg++)
#pragma unroll
        for (int bk = 3; bk >= kap; bk--) {
          const uint32_t(&q0_)[4] = f3[sg ? 2 : 0][bk - kap];
          const uint32_t(&q1_)[4] = f3[sg ? 2 : 1][bk - kap];
          float(&a0)[4] = a[bk][0];
          float(&a1)[4] = a[bk][1];
          if (sg == 0 && kap == 0) {
            mma0(a0[0], a0[1], a0[2], a0[3], q0_[0], q0_[1], q0_[2], q0_[3], z09[0], z09[1]);
            mma0(a1[0], a1[1], a1[2], a1[3], q1_[0], q1_[1], q1_[2], q1_[3], zm9[0], zm9[1]);
          } else {
            mma(a0[0], a0[1], a0[2], a0[3], q0_[0], q0_[1], q0_[2], q0_[3], sg ? zm7[2 * kap] : z09[2 * kap], sg ? zm7[2 * kap + 1] : z09[2 * kap + 1]);
            mma(a1[0], a1[1], a1[2], a1[3], q1_[0], q1_[1], q1_[2], q1_[3], sg ? z07[2 * kap] : zm9[2 * kap], sg ? z07[2 * kap + 1] : zm9[2 * kap + 1]);
          }
        }
    SPLIT();
#pragma unroll
    for (int i = 0; i < 8; i++) {
      uint32_t h[4];
      ldsm4(h, qa + 128 * i);
      const float ci[4] = {a[i >> 1][0][2 * (i & 1)], a[i >> 1][0][2 * (i & 1) + 1], a[i >> 1][1][2 * (i & 1)], a[i >> 1][1][2 * (i & 1) + 1]};
      mmac(acc[8 + i], h[0], h[1], h[2], h[3], lb0, lb1, ci);
    }
  }
  TS(44);
  {
    uint2 a5[10], a3[10];
    const uint32_t aa = tb + T_5 + 4 * (8 + 2 * g - 2 * c);
#pragma unroll
    for (int m = 0; m < 10; m++) { a5[m] = lds64(aa + 32 * m); a3[m] = lds64(aa + 384 + 32 * m); }
    uint32_t x5[12][2], x3[12][2];
    auto ygen = [&](int kap) {
#pragma unroll
      for (int hh = 0; hh < 2; hh++) {
        float y0, y1, y2, y3;
        mma0(y0, y1, y2, y3, by[0], by[1], by[2], by[3], lds32(y0a + 128 * kap + 64 * hh), lds32(y1a + 128 * kap + 64 * hh));
        x5[kap][hh] = pack_bf(y0, y1);
        x3[kap][hh] = pack_bf(y2, y3);
      }
    };
    ygen(11); ygen(10); ygen(9); ygen(8);
#pragma unroll
    for (int kap = 11; kap >= 0; kap--) {
      if (kap >= 4) ygen(kap - 4);
#pragma unroll
      for (int sg = 0; sg < 2; sg++)
#pragma unroll
        for (int i = 4; i >= 0; i--) {
          const int be = kap + 4 + i;
          if (be <= 15) {
            const uint2 &hi = sg ? a3[2 * i + 1] : a5[2 * i + 1], &lo = sg ? a3[2 * i] : a5[2 * i];
            const uint32_t b0 = sg ? x3[kap][0] : x5[kap][0], b1 = sg ? x3[kap][1] : x5[kap][1];
            if (be < 8 && i == 0 && sg == 0) mma0(acc[be][0], acc[be][1], acc[be][2], acc[be][3], hi.x, hi.y, lo.x, lo.y, b0, b1);
            else mma(acc[be][0], acc[be][1], acc[be][2], acc[be][3], hi.x, hi.y, lo.x, lo.y, b0, b1);
          }
        }
    }
  }
  TS(45);
  {
    const uint32_t st = tb + T_ST + lane * 8;
#pragma unroll
    for (int be = 4; be < 12; be++) sts64(st + 256 * be, pack_bf(acc[be][0], acc[be][1]), pack_bf(acc[be][2], acc[be][3]));
    SPLIT();
    uint32_t F[66], qd[8][4];
    const uint32_t fa = tb + T_D + 32 + 4 * x;
#pragma unroll
    for (int i = 0; i < 32; i++) {
      const int s = 120 - (i >> 2) - 8 * (i & 3);
      uint32_t(&q)[4] = qd[i & 7];
      ldsm4(q, qa + 16 * s);
      const int m = 16 * (i & 3) + 2 * (i >> 2);
      F[m] = lds32(fa + 32 * m); F[m + 1] = lds32(fa + 32 * m + 32);
#pragma unroll
      for (int be = 15; be >= 12; be--) {
        const int de = 8 * be - s;
        float(&a)[4] = (be >= 14 && !(i & 1)) ? acc[be - 4] : acc[be];
        if (de >= 0 && be >= 14 && i == 2 * (15 - be)) mma0(a[0], a[1], a[2], a[3], q[0], q[1], q[2], q[3], F[2 * de + 1], F[2 * de]);
        else if (de >= 0) mma(a[0], a[1], a[2], a[3], q[0], q[1], q[2], q[3], F[2 * de + 1], F[2 * de]);
      }
    }
#pragma unroll
    for (int i = 0; i < 8; i++) acc[14 + (i >> 2)][i & 3] += acc[10 + (i >> 2)][i & 3];
    F[64] = lds32(fa + 32 * 64); F[65] = lds32(fa + 32 * 65);
#pragma unroll
    for (int i = 0; i < 6; i++) ldsm4(qd[i], qa + 128 * 11 - 16 * i);
    uint2 sv = lds64(st + 256 * 11);
    float ci[4] = {bf_lo(sv.x), bf_hi(sv.x), bf_lo(sv.y), bf_hi(sv.y)};
    float T[5][4];
#pragma unroll
    for (int i = 0; i < 16; i++) T[i >> 2][i & 3] = acc[12 + (i >> 2)][i & 3];
    nb_sync(NB_YZ, 160);
    TS(46);
    uint32_t held[2];
#pragma unroll
    for (int be = 11; be >= 0; be--) {
      if (be & 1) SPLITN(be);
      const uint32_t qp = qa + 128 * be;
#pragma unroll
      for (int k = 4; k >= 1; k--) mmac(T[k], qd[0][0], qd[0][1], qd[0][2], qd[0][3], F[16 * k + 1], F[16 * k], T[k - 1]);
      if (be >= 4) mmac(T[0], qd[0][0], qd[0][1], qd[0][2], qd[0][3], F[1], F[0], ci);
      else mma0(T[0][0], T[0][1], T[0][2], T[0][3], qd[0][0], qd[0][1], qd[0][2], qd[0][3], F[1], F[0]);
      ldsm4(qd[6], qp - 16 * 6);
      ldsm4(qd[7], qp - 16 * 7);
      if (be > 4) sv = lds64(st + 256 * (be - 1));
#pragma unroll
      for (int i = 1; i < 8; i++) {
#pragma unroll
        for (int k = 3; k >= 0; k--)
          mma(T[k][0], T[k][1], T[k][2], T[k][3], qd[i][0], qd[i][1], qd[i][2], qd[i][3], F[16 * k + 2 * i + 1], F[16 * k + 2 * i]);
        if (i < 7 && be > 0) ldsm4(qd[i - 1], qp - 128 - 16 * (i - 1));
        if (i == 2) {
          const uint32_t w0 = pack_bf(T[4][0], T[4][1]), w1 = pack_bf(T[4][2], T[4][3]);
          if (be & 1) { held[0] = w0; held[1] = w1; }
          else st_x(ydst + (be + 4) * 16, nz(w0), w1, held[0], held[1]);
          if ((be & 3) == 3 && be < 11) nb_arrive(NB_Y + 2 + (be >> 2), 160);
        }
        if (i == 4 && be > 4) { ci[0] = bf_lo(sv.x); ci[1] = bf_hi(sv.x); ci[2] = bf_lo(sv.y); ci[3] = bf_hi(sv.y); }
      }
    }
    nb_arrive(NB_Y + 1, 160);
#pragma unroll
    for (int B = 1; B >= 0; B--)
      st_x(ydst + B * 32, nz(pack_bf(T[2 * B][0], T[2 * B][1])), pack_bf(T[2 * B][2], T[2 * B][3]),
           pack_bf(T[2 * B + 1][0], T[2 * B + 1][1]), pack_bf(T[2 * B + 1][2], T[2 * B + 1][3]));
  }
}

__device__ __forceinline__ void dual_exp(const uint32_t* w, uint32_t* e) {
  const float L = 1.44268798828125f;
  uint32_t mx = bmax2(bmax2(w[0], w[1]), bmax2(w[2], w[3]));
  uint32_t mn = bmin2(bmin2(w[0], w[1]), bmin2(w[2], w[3]));
  mx = bmax2(mx, __shfl_xor_sync(0xffffffffu, mx, 1));
  mn = bmin2(mn, __shfl_xor_sync(0xffffffffu, mn, 1));
  mx = bmax2(mx, __shfl_xor_sync(0xffffffffu, mx, 2));
  mn = bmin2(mn, __shfl_xor_sync(0xffffffffu, mn, 2));
  const float mx0 = bf_lo(mx) * -L, mx1 = bf_hi(mx) * -L, mn0 = bf_lo(mn) * L, mn1 = bf_hi(mn) * L;
#pragma unroll
  for (int i = 0; i < 2; i++) {
    const float a0 = bf_lo(w[2 * i]), a1 = bf_hi(w[2 * i]), b0 = bf_lo(w[2 * i + 1]), b1 = bf_hi(w[2 * i + 1]);
    e[2 * i] = pack_bf(ex2(fmaf(a0, L, mx0)), ex2(fmaf(b0, L, mx0)));
    e[2 * i + 1] = pack_bf(ex2(fmaf(a1, L, mx1)), ex2(fmaf(b1, L, mx1)));
    e[4 + 2 * i] = pack_bf(ex2(fmaf(a0, -L, mn0)), ex2(fmaf(b0, -L, mn0)));
    e[5 + 2 * i] = pack_bf(ex2(fmaf(a1, -L, mn1)), ex2(fmaf(b1, -L, mn1)));
  }
}
__device__ __forceinline__ void normalise(uint32_t* e, const float (&s)[4]) {
  const uint32_t r = pack_bf(rcp(s[0]), rcp(s[2]));
  const __nv_bfloat162 rr = *(const __nv_bfloat162*)&r;
#pragma unroll
  for (int i = 0; i < 4; i++) {
    const __nv_bfloat162 v = __hmul2(*(const __nv_bfloat162*)&e[i], (i & 1) ? __high2bfloat162(rr) : __low2bfloat162(rr));
    e[i] = *(const uint32_t*)&v;
  }
}
__host__ __device__ constexpr uint64_t qdesc(uint32_t addr) { return mkdesc(addr, 128, 256, 0); }

__global__ void __launch_bounds__(NTHREADS, 1)
fused_kernel(const Params P, const __grid_constant__ CUtensorMap mx, const __grid_constant__ CUtensorMap mw,
             const __grid_constant__ CUtensorMap mo, const __grid_constant__ CUtensorMap mu,
             const __grid_constant__ CUtensorMap mout) {
  constexpr uint32_t sb = SB;
  const int tid = threadIdx.x, lane = tid & 31;
  const int warp = __shfl_sync(0xffffffffu, tid >> 5, 0);
  const int b = blockIdx.x, oct = b >> 3, i8 = b & 7;
  const int rt = (((oct & 4) ? ~oct : oct) & 3) * 2 + (i8 >> 2);
  const int hp = (oct >> 2) * 4 + (i8 & 3);

  const int wg = warp >> 2, w = warp & 3;
  const int d = b * 4 + ((tid >> 5) & 3);
  const KgenRaw raw = kgen_load(P, d, (tid >> 7) & 1, lane, (tid + 128) & 256);
  const uint32_t tb = sb + OFF_T + w * T_CH;
  if (warp >= 12) {
    asm volatile("setmaxnreg.dec.sync.aligned.u32 32;");
    if (warp == 12) {
      if (lane == 0) {
#pragma unroll
        for (int i = 0; i < 9; i++) mbar_init(BAR(i), 1);
        asm volatile("fence.mbarrier_init.release.cluster;" ::: "memory");
      }
      __syncwarp();
      if (lane < 9) mbar_expect(BAR(0) + 8 * lane, lane == 0 ? 16384 : 28672);
      __syncwarp();
      nb_arrive(NB_PROD, 384);
#pragma unroll 1
      for (int kb = 0; kb < 8; kb++) {
        if (kb == U_AT) e_tma4d(sb + OFF_STG0, &mu, BAR(MB_URAW), i8 * 64, oct * 2);
        e_tma3d(sb + OFF_W + kb * 12288, &mw, BAR(MB_FULL) + 8 * kb, hp * 32, kb * 64, 0);
        if (kb < 5) e_tma2d(sb + OFF_X + (kb < 2 ? kb + 3 : kb - 2) * 16384, &mx, BAR(MB_FULL) + 8 * kb, kb * 64, rt * 256);
      }
      if (smem_u32(smem_raw) != SB) __trap();
      if (lane == 0) TS1(54);
      nb_sync(NB_GATE + 1, 64);
      if (X2_AT < 0) e_prefetch(P.x + (size_t)(rt * 256 + 128 + hp * 8) * 512, 8192);
      uint32_t slot = sb + OFF_X + 3 * 16384;
#pragma unroll 1
      for (int n = 0; n < 11; n++) {
        mbar_spin(BAR(MB_EMPTY) + 8 * n);
        const int m = n + 5;
        e_tma2d(slot, &mx, BAR(MB_FULL) + 8 * m, (m & 7) * 64, rt * 256 + (m >> 3) * 128);
        slot = slot == sb + OFF_X + 4 * 16384 ? sb + OFF_X : slot + 16384;
        if (n == X2_AT) e_prefetch(P.x + (size_t)(rt * 256 + 128 + hp * 8) * 512, 8192);
        if (n == 7) {
          e_prefetch(P.wo + (size_t)b * 2048, 4096);
          asm volatile("prefetch.tensormap [%0];" ::"l"(&mo) : "memory");
          asm volatile("prefetch.tensormap [%0];" ::"l"(&mout) : "memory");
        }
      }
#pragma unroll 1
      for (int i = 0; i < 8; i++) {
        mbar_wait(BAR(MB_EMPTY + 10) + 8 * ((0x54332222u >> (4 * i)) & 7));
        const int w0 = (0x54736210u >> (4 * i)) & 7;
        e_tma3d(sb + OFF_W + w0 * 16384, &mo, BAR(MB_WO), 0, w0 * 64, (hp & 3) * 2);
      }
    } else {
      if (warp == 13) {
        if (lane == 0) {
#pragma unroll
          for (int i = 9; i < 40; i++) mbar_init(BAR(i), i < MB_EMPTY ? 1 : 4);
          asm volatile("fence.mbarrier_init.release.cluster;" ::: "memory");
        }
        __syncwarp();
        if (lane < 14 && lane != 9) mbar_expect(BAR(MB_FULL + 8) + 8 * lane, lane == 8 ? 131072 : (lane == 10 ? 8192 : (lane == 13 ? 24576 : 16384)));
        nb_arrive(NB_GATE + 1, 64);
      } else if (warp == 14) {
        asm volatile("prefetch.tensormap [%0];" ::"l"(&mw) : "memory");
        asm volatile("prefetch.tensormap [%0];" ::"l"(&mx) : "memory");
        asm volatile("prefetch.tensormap [%0];" ::"l"(&mu) : "memory");
        e_prefetch(P.x + (size_t)(rt * 256 + hp * 8) * 512, 8192);
      }
      nb_sync(NB_PROD, 384);
      if (warp == 15) {
        const uint4 v0 = __ldg((const uint4*)P.wphi + hp * 64 + lane), v1 = __ldg((const uint4*)P.wphi + hp * 64 + 32 + lane);
        sts128(sb + OFF_PHI + (lane & 1) * 256 + (lane >> 1) * 16, v0.x, v0.y, v0.z, v0.w);
        sts128(sb + OFF_PHI + 512 + (lane & 1) * 256 + (lane >> 1) * 16, v1.x, v1.y, v1.z, v1.w);
        const uint32_t one = (((lane >> 3) ^ (lane >> 4)) & 1) ? 0u : ((lane & 1) ? 0x3F800000u : 0x3F80u);
        const int q = (lane >> 1) & 3;
        sts128(sb + OFF_EYE + lane * 16, q == 0 ? one : 0u, q == 1 ? one : 0u, q == 2 ? one : 0u, q == 3 ? one : 0u);
        sts64(sb + OFF_ONE + lane * 8, 0x3F803F80u, 0x3F803F80u);
        asm volatile("fence.proxy.async.shared::cta;" ::: "memory");
        nb_arrive(NB_KREAD, 160);
      }
      uint32_t* cnt = (uint32_t*)(P.xs + X_CNT) + (warp == 13 ? i8 : (warp == 14 ? 8 + rt : 16 + oct)) * 32;
      const unsigned target = (ld_x32(cnt) & ~15u) + 16;
      if (warp != 14) {
        if (warp == 15) mbar_wait(BAR(MB_EMPTY + ZERO_STEP));
        uint4* pz = P.xs + (warp == 13 ? X_PART + (hp * 8 + rt) * 144 : X_Y + b * 1024) + lane;
#pragma unroll 1
        for (int i = (warp == 13 ? 144 : 1024) - lane; i > 0; i -= 32, pz += 32) st_x(pz, 0, 0, 0, 0);
      }
      if (warp == 15) __syncwarp();
      else nb_sync(warp == 13 ? NB_INIT : NB_ODONE, warp == 13 ? 160 : 288);
      if (lane == 0) asm volatile("red.release.gpu.global.add.u32 [%0], %1;" ::"l"(cnt), "r"(warp == 15 ? 2 : 1) : "memory");
      if (lane == 0) TS1(warp == 13 ? 50 : (warp == 14 ? 57 : 53));
      __syncwarp();
      if (warp == 14) nb_arrive(NB_GATE + 1, 160);
      asm volatile("fence.proxy.async.shared::cta;" ::: "memory");
      if (warp == 13) cnt += ((lane & 1 ? b >> 4 : i8 ^ (lane & 4)) - i8) * 32;
#pragma unroll 1
      for (int i = 0; i < SPIN_MAX; i++) {
        unsigned v;
        asm volatile("ld.acquire.gpu.global.u32 %0, [%1];" : "=r"(v) : "l"(cnt) : "memory");
        if (__all_sync(0xffffffffu, (int)(v - target) >= 0)) break;
      }
      if (lane == 0) TS1(warp == 13 ? 51 : (warp == 14 ? 58 : 55));
      if (warp == 15) { nb_arrive(NB_YZ, 160); return; }
      asm volatile("fence.proxy.async.global;" ::: "memory");
      if (warp == 13) {
        mbar_wait(BAR(MB_EMPTY + 11));
        e_expect(BAR(MB_UFULL), 4 * U_CH);
        e_bulk(sb + OFF_U, P.xs + X_UT + b * (U_CH / 4), 4 * U_CH, BAR(MB_UFULL));
      } else {
        const uint4* src = P.xs + X_O + (rt * 4 + (hp >> 2)) * 4096;
        e_bulk(sb + OFF_X + 32768 + 57344, src + 3584, 8192, BAR(MB_O));
        e_bulk(sb + OFF_X + 32768, src, 16384, BAR(MB_O + 1));
        e_bulk(sb + OFF_X + 49152, src + 1024, 16384, BAR(MB_O + 2));
        e_bulk(sb + OFF_STG0, src + 3200, 6144, BAR(MB_O + 3));
        nb_sync(NB_BDONE, 288);
        asm volatile("fence.proxy.async.shared::cta;" ::: "memory");
        e_bulk(sb + OFF_U, src + 2048, 18432, BAR(MB_O + 3));
      }
    }
    return;
  }

  asm volatile("setmaxnreg.inc.sync.aligned.u32 160;");
  const int t = tid & 127;
  const int g = lane >> 2, c = lane & 3;
  const uint32_t kp = wg ? ((tb + 127) & ~127u) + (wg & 1) * 2048 : sb + OFF_STG0 + 16384 + w * 2048;
  const KgenAddr kad = kgen_addr(lane, kp);
  if (wg) nb_sync(NB_PROD, 384);
  float k[5][4], k2048, ksc;
  if (wg || w < WARM_K) {
    kgen_unit(raw, kad, blockIdx.y, k, k2048, ksc);
    TS(40 + wg);
    if ((fu(k[0][0]) & fu(k[1][0]) & fu(k[2][0]) & fu(k[3][0]) & fu(k[4][0])) == 0xffffffffu) sts32(kp, 0);
  }
  if (wg) nb_arrive(0, 384);
  if (wg) {
    if (wg == 1) {
      uint32_t h[10];
#pragma unroll
      for (int j = 0; j < 10; j++) h[j] = hu(__floats2half2_rn(k[j >> 1][2 * (j & 1)], k[j >> 1][2 * (j & 1) + 1]));
      sts128(kp + lane * 16, h[0], h[1], h[2], h[3]);
      sts128(kp + 512 + lane * 16, h[4], h[5], h[6], h[7]);
      sts128(kp + 1024 + lane * 16, h[8], h[9], fu(k2048), fu(ksc));
      nb_arrive(NB_PREP, 256);
    }
  } else {
    nb_sync(NB_KREAD, 160);
    nb_sync(0, 384);
  }
  if (wg == 1) {
    mbar_wait(BAR(MB_URAW));
    TS(48);
    uint4* dst = P.xs + X_UT + (i8 * 64 + g) * (U_CH / 16) + (w & 1) * (U_ODD / 16) + U_PAD / 16 + oct * 8 + (w >> 1) * 4 + c;
    const int ln = ((lane >> 1) & 3) + 4 * (lane & 1);
    uint32_t r[8][4];
#pragma unroll
    for (int i = 0; i < 8; i++) ldsm4t(r[i], sb + OFF_STG0 + w * 4096 + ((lane >> 3) * 8 + ln) * 128 + ((i ^ ln) << 4));
#pragma unroll
    for (int i = 0; i < 8; i++) dst[i * (U_CH / 2)] = make_uint4(r[i][0], r[i][1], r[i][2], r[i][3]);
    nb_arrive(NB_INIT, 160);
    if (lane == 0) mbar_arrive(BAR(MB_AUX));
  }
  {
    if (wg == 2) {
#pragma unroll
      for (int j = 0; j < 5; j++) { k[j][0] *= ksc; k[j][1] *= ksc; k[j][2] *= ksc; k[j][3] *= ksc; }
      const unsigned short dsk = __ldg((const unsigned short*)P.Dskip + d);
      nb_sync(NB_PREP, 256);
      {
        const uint32_t src = kp + 2048 + lane * 16;
        const uint4 v0 = lds128(src), v1 = lds128(src + 512), v2 = lds128(src + 1024);
        const uint32_t h[10] = {v0.x, v0.y, v0.z, v0.w, v1.x, v1.y, v1.z, v1.w, v2.x, v2.y};
#pragma unroll
        for (int j = 0; j < 10; j++) {
          const float2 f = __half22float2(*(const __half2*)&h[j]);
          k[j >> 1][2 * (j & 1)] = fmaf(f.x, uf(v2.w), k[j >> 1][2 * (j & 1)]);
          k[j >> 1][2 * (j & 1) + 1] = fmaf(f.y, uf(v2.w), k[j >> 1][2 * (j & 1) + 1]);
        }
        k2048 += uf(v2.z);
      }
#pragma unroll
      for (int o2 = 16; o2; o2 >>= 1) k2048 += __shfl_xor_sync(0xffffffffu, k2048, o2);
      if (lane == 0) k[0][0] += bf_lo(dsk);
      __syncwarp();
      TS(34);
      build_tables(tb, lane, k, k2048);
      TS(35);
      uint4* const g_y = P.xs + X_Y;
      conv_channel(sb + OFF_U + w * U_CH, tb, lane, g_y + (size_t)d * 256 + lane);
      nb_arrive(NB_BDONE, 288);
      nb_arrive(NB_Y, 160);
      TS(37);
      if (w == 0) TSDUMP(32);
      return;
    }
    if (wg == 1) {
      mbar_wait(BAR(MB_EMPTY + 4));
      mbar_spin(BAR(MB_EMPTY + 6));
    }
    TS(wg * 16 + 1);
  }

  float acc[2][48];
  {
    uint32_t fb = BAR(MB_FULL) + 64 * wg;
    uint32_t da = (uint32_t)mkdesc(sb + OFF_X, 16, 0, 0) + (wg ? 1024 : 3072), db = (uint32_t)mkdesc(sb + OFF_W, 4096, 0, 0);
    constexpr uint64_t ha = mkdesc(0, 0, 1024, 1), hb = mkdesc(0, 0, 512, 2);
    mbar_spin(fb);
    TS(wg * 16 + 2);
#pragma unroll 1
    for (int kb = 0; kb < 8; kb++) {
      WG_FENCE();
#pragma unroll
      for (int k = 0; k < 4; k++) {
        wgmma_ss_n96(acc[0], ha | (da + 2 * k), hb | (db + 64 * k), k ? 1 : kb);
        wgmma_ss_n96(acc[1], ha | (da + 2 * k + 512), hb | (db + 64 * k), k ? 1 : kb);
      }
      WG_COMMIT();
      if (kb < 7) mbar_spin(fb + 8);
      WG_WAIT(1);
      if (kb > 0) e_arrive(fb + 8 * (MB_EMPTY - MB_FULL - 1));
      fb += 8; db += 768;
      da = da == (uint32_t)mkdesc(sb + OFF_X + 65536, 16, 0, 0) ? da - 4096 : da + 1024;
    }
    WG_WAIT(0);
    e_arrive(fb + 8 * (MB_EMPTY - MB_FULL - 1));
    SPLIT();
  }
  TS(wg * 16 + 3);

  constexpr uint32_t stg0 = sb + OFF_STG0, stg1 = sb + OFF_X + 32768;
  uint4* const g_part = P.xs + X_PART;
  uint4* const g_o = P.xs + X_O;
  constexpr uint32_t kvs = stg0;
  auto pack8 = [](const float* a) { return make_uint4(pack_bf(a[0], a[1]), pack_bf(a[2], a[3]), pack_bf(a[4], a[5]), pack_bf(a[6], a[7])); };
  auto feat = [&](const uint4 (&af)[4], float (&p)[4][8]) {
    WG_FENCE();
#pragma unroll
    for (int u = 0; u < 4; u++) wgmma_rs_n16(p[u], af[u], qdesc(sb + OFF_PHI + (u & 1) * 512), 0);
    WG_COMMIT();
  };
  auto packp = [](const float (&p)[4][8], uint32_t (&pw)[16]) {
#pragma unroll
    for (int i = 0; i < 16; i++) pw[i] = pack_bf(p[i >> 2][(i & 1) + 2 * (i & 2)], p[i >> 2][(i & 1) + 2 * (i & 2) + 2]);
  };
  auto contract = [&](float (&kc)[20], uint32_t stg, int acc_in) {
    WG_FENCE();
#pragma unroll
    for (int s = 0; s < 8; s++) wgmma_ss_n40(kc, qdesc(stg + s * SLAB), qdesc(stg + s * SLAB + 2048), s ? 1 : acc_in);
    WG_COMMIT();
    WG_WAIT(0);
  };
  uint32_t eq[32];
  {
    uint4 af[4], aq[4], vp[4];
    float p[4][8];
#pragma unroll
    for (int u = 0; u < 4; u++) af[u] = pack8(acc[u >> 1] + 16 + 8 * (u & 1));
    feat(af, p);
#pragma unroll
    for (int u = 0; u < 4; u++) { aq[u] = pack8(acc[u >> 1] + 8 * (u & 1)); vp[u] = pack8(acc[u >> 1] + 32 + 8 * (u & 1)); }
    WG_WAIT(0);
    uint32_t pw[16], ek[32];
    packp(p, pw);
#pragma unroll
    for (int u = 0; u < 4; u++) dual_exp(pw + 4 * u, ek + 8 * u);
    TS(wg * 16 + 12);
    mbar_spin(wg ? BAR(MB_EMPTY + 15) : BAR(MB_AUX));
    float rs[8][4];
    WG_FENCE();
#pragma unroll
    for (int i = 0; i < 8; i++) wgmma_rs_n8(rs[i], make_uint4(ek[4 * i], ek[4 * i + 1], ek[4 * i + 2], ek[4 * i + 3]), qdesc(sb + OFF_ONE), 0);
    WG_COMMIT();
    feat(aq, p);
    const uint32_t sl = (wg ? stg1 : stg0) + w * SLAB + lane * 16;
#pragma unroll
    for (int i = 0; i < 4; i++) stsm4(sl + (i >> 1) * 4 * SLAB + 2048 + (i & 1) * 512, vp[i].x, vp[i].y, vp[i].z, vp[i].w);
    sts128(sl + (lane >> 4) * (4 * SLAB - 256) + 3072, 0x3F803F80u, 0x3F803F80u, 0x3F803F80u, 0x3F803F80u);
    WG_WAIT(1);
#pragma unroll
    for (int i = 0; i < 8; i++) {
      normalise(ek + 4 * i, rs[i]);
      stsm4(sl + (i >> 2) * 4 * SLAB + (i & 3) * 512, ek[4 * i], ek[4 * i + 1], ek[4 * i + 2], ek[4 * i + 3]);
    }
    asm volatile("fence.proxy.async.shared::cta;" ::: "memory");
    TS(wg * 16 + 13);
    if (wg) {
      nb_arrive(NB_ST0, 256);
      nb_arrive(NB_GATE, 256);
    } else {
      float kc[20];
      uint4* pp = g_part + (size_t)(hp * 8 + rt) * 144 + t;
      uint32_t* pz = (uint32_t*)(pp - t + 128) + w * 16 + c * 8 + g;
      asm volatile("" : "+l"(pp), "+l"(pz));
      nb_sync(NB_WG0, 128);
      contract(kc, stg0, 0);
      mbar_wait(BAR(MB_UFULL));
      TS(15);
      nb_sync(NB_ST0, 256);
      contract(kc, stg1, 1);
      TS(6);
      float kv[8];
#pragma unroll
      for (int i = 0; i < 8; i++) kv[i] = w & 2 ? kc[8 + i] : kc[i];
      st_x(pp, nz(pack_bf(kv[0], kv[1])), pack_bf(kv[2], kv[3]), pack_bf(kv[4], kv[5]), pack_bf(kv[6], kv[7]));
      if (c < 2) st_x32(pz, nz(fu(c ? kc[18] : kc[16])));
      TS(5);
    }
    SPLIT();
    WG_WAIT(0);
    packp(p, pw);
#pragma unroll
    for (int u = 0; u < 4; u++) dual_exp(pw + 4 * u, eq + 8 * u);
    SPLIT();
  }
  TS(wg * 16 + 4);
  if (wg == 1) {
    mbar_wait(BAR(MB_UFULL));
    const uint4* ps = g_part + (size_t)hp * 8 * 144 + t;
    const uint32_t* zs = (const uint32_t*)(g_part + (size_t)(hp * 8 + (lane >> 4) * 4) * 144 + 128) + w * 16 + (lane & 15);
    uint4 v[8];
    uint32_t zv[4];
#pragma unroll 1
    for (int it = 0; it < SPIN_MAX; it++) {
#pragma unroll
      for (int i = 0; i < 8; i++) v[i] = ld_x(ps + i * 144);
#pragma unroll
      for (int i = 0; i < 4; i++) zv[i] = ld_x32(zs + i * 576);
      uint32_t m = min(min(zv[0], zv[1]), min(zv[2], zv[3]));
#pragma unroll
      for (int i = 0; i < 8; i++) m = min(m, v[i].x);
      if (__all_sync(0xffffffffu, m != 0)) break;
    }
    float s[8];
    WG_FENCE();
#pragma unroll
    for (int r = 0; r < 8; r++) wgmma_rs_n16(s, v[r], qdesc(sb + OFF_EYE), r);
    WG_COMMIT();
    float zsum = (uf(zv[0]) + uf(zv[1])) + (uf(zv[2]) + uf(zv[3]));
    zsum += __shfl_xor_sync(0xffffffffu, zsum, 16);
    const uint32_t z1 = pack_bf(zsum, 1.f);
    if (lane < 16) sts128(kvs + w * 768 + 512 + lane * 16, z1, z1, z1, z1);
    WG_WAIT(0);
    stsm4(kvs + w * 768 + lane * 16, pack_bf(s[0], s[1]), pack_bf(s[2], s[3]), pack_bf(s[4], s[5]), pack_bf(s[6], s[7]));
    asm volatile("fence.proxy.async.shared::cta;" ::: "memory");
    TS(22);
  }
  nb_sync(NB_KV, 256);
  {
    float n[8][12];
    WG_FENCE();
#pragma unroll
    for (int i = 0; i < 8; i++) wgmma_rs_n24(n[i], make_uint4(eq[4 * i], eq[4 * i + 1], eq[4 * i + 2], eq[4 * i + 3]), qdesc(kvs + (i & 3) * 768), 0);
    WG_COMMIT();
    uint32_t* od = (uint32_t*)(g_o + (size_t)((rt * 4 + wg * 2) * 32 + hp * 2) * 128) + w * 64 + lane;
    WG_WAIT(0);
#pragma unroll
    for (int u = 0; u < 4; u++) {
      float(&np)[12] = n[2 * u];
      const float(&nm)[12] = n[2 * u + 1];
      const float q0 = np[9] * rcp(nm[9]), q1 = np[11] * rcp(nm[11]);
      const float r0 = rcp(fmaf(nm[8], q0, fmaf(np[9], 1e-6f, np[8]))), r1 = rcp(fmaf(nm[10], q1, fmaf(np[11], 1e-6f, np[10])));
#pragma unroll
      for (int i = 0; i < 8; i++) np[i] = fmaf(nm[i], (i & 2) ? q1 : q0, np[i]);
      uint32_t* o = od + (u >> 1) * 16384 + (u & 1) * 512;
      o[0] = pack_bf(np[0] * r0, np[1] * r0);
      o[32] = pack_bf(np[2] * r1, np[3] * r1);
      o[256] = pack_bf(np[4] * r0, np[5] * r0);
      o[288] = pack_bf(np[6] * r1, np[7] * r1);
      if (u == 1) SPLIT();
    }
  }
  TS(wg * 16 + 7);
  nb_arrive(NB_ODONE, 288);
  if (wg) {
    const uint4* src = P.xs + X_Y + (oct * 32 + c * 8) * 256 + (2 * w + (g >> 2)) * 32 + i8 * 4 + (g & 3);
    __nv_bfloat16* dst = P.out + (size_t)((2 * w + (g >> 2)) * 256 + i8 * 16 + (g & 3) * 2) * 1024 + 512 + oct * 32 + c * 8;
    nb_sync(NB_GATE + 1, 160);
    nb_sync(NB_Y + w, 160);
    uint4 v[8];
#pragma unroll 1
    for (int it = 0; it < SPIN_MAX; it++) {
      uint32_t m = 0xffffffffu;
#pragma unroll
      for (int i = 0; i < 8; i++) v[i] = ld_x(src + i * 256);
#pragma unroll
      for (int i = 0; i < 8; i++) m = min(m, v[i].x);
      if (__all_sync(0xffffffffu, m != 0)) break;
    }
#pragma unroll
    for (int i = 0; i < 8; i++) *(uint4*)(dst + (size_t)((i >> 2) * 128 + ((i >> 1) & 1) * 8 + (i & 1)) * 1024) = tr_row(v, i);
    TS(31);
    GT(63);
    if (w == 0) TSDUMP(16);
    return;
  }
  mbar_wait(BAR(MB_WO));
  nb_sync(NB_BDONE, 288);
  TS(8);
  mbar_spin(BAR(MB_O));
  TS(9);
  constexpr uint64_t ha = mkdesc(0, 0, 128, 0), hb = mkdesc(0, 0, 1024, 1);
  constexpr uint32_t da0 = (uint32_t)mkdesc(stg1, 1024, 0, 0), db0 = (uint32_t)mkdesc(sb + OFF_W, 8192, 0, 0);
  const uint32_t ot = ((sb + OFF_T + 1023) & ~1023u) + w * 4096;
  auto store_half = [&](const float* oc, int hf) {
#pragma unroll
    for (int i = 0; i < 8; i += 2)
      stsm4(ot + hf * 2048 + (lane & 15) * 128 + (((i + (lane >> 4)) ^ lane) & 7) * 16, pack_bf(oc[4 * i], oc[4 * i + 1]),
            pack_bf(oc[4 * i + 2], oc[4 * i + 3]), pack_bf(oc[4 * i + 4], oc[4 * i + 5]), pack_bf(oc[4 * i + 6], oc[4 * i + 7]));
    asm volatile("fence.proxy.async.shared::cta;" ::: "memory");
    __syncwarp();
    e_store2d(&mout, ot + hf * 2048, (hp & 3) * 128 + hf * 64, (rt * 4 + (hp >> 2)) * 64 + w * 16);
  };
  float oc[64];
#pragma unroll 1
  for (int j = 0; j < 8; j++) {
    const int kb = (j + 7) & 7;
    if ((j & 1) && j < 6) mbar_spin(BAR(MB_O + 1) + 4 * (j - 1));
    WG_FENCE();
#pragma unroll
    for (int k = 0; k < 4; k++) wgmma_ss_n128(oc, ha | (da0 + 512 * kb + 128 * k), hb | (db0 + 1024 * kb + 128 * k), k ? 1 : j);
    WG_COMMIT();
  }
  WG_WAIT(0);
  TS(10);
  store_half(oc, 0);
  store_half(oc + 32, 1);
  asm volatile(ELECT "cp.async.bulk.commit_group;\n@p cp.async.bulk.wait_group.read 0;\n}\n" ::: "memory");
  TS(wg * 16 + 11);
  GT(61 + wg);
  if (w == 0) TSDUMP(0);
  if (w == 1) TSDUMP(48);
}

typedef CUresult (*EncodeFn)(CUtensorMap*, CUtensorMapDataType, cuuint32_t, void*, const cuuint64_t*, const cuuint64_t*,
                             const cuuint32_t*, const cuuint32_t*, CUtensorMapInterleave, CUtensorMapSwizzle,
                             CUtensorMapL2promotion, CUtensorMapFloatOOBfill);

}

extern "C" void kernel_launch(void* const* d_in, const int* in_sizes, int n_in, void* d_out, int out_size) {
  (void)in_sizes; (void)n_in; (void)out_size;
  void* fn = nullptr;
  cudaDriverEntryPointQueryResult qr;
  cudaGetDriverEntryPoint("cuTensorMapEncodeTiled", &fn, cudaEnableDefault, &qr);
  EncodeFn enc = (EncodeFn)fn;
  CUtensorMap mx, mw, mo, mu, mout;
  const cuuint32_t es[5] = {1, 1, 1, 1, 1};
  {
    cuuint64_t dims[2] = {512, 2048}, st[1] = {1024};
    cuuint32_t box[2] = {64, 128};
    enc(&mx, CU_TENSOR_MAP_DATA_TYPE_BFLOAT16, 2, d_in[0], dims, st, box, es, CU_TENSOR_MAP_INTERLEAVE_NONE,
        CU_TENSOR_MAP_SWIZZLE_128B, CU_TENSOR_MAP_L2_PROMOTION_L2_128B, CU_TENSOR_MAP_FLOAT_OOB_FILL_NONE);
  }
  {
    cuuint64_t dims[3] = {512, 512, 3}, st[2] = {3072, 1024};
    cuuint32_t box[3] = {32, 64, 3};
    enc(&mw, CU_TENSOR_MAP_DATA_TYPE_BFLOAT16, 3, d_in[1], dims, st, box, es, CU_TENSOR_MAP_INTERLEAVE_NONE,
        CU_TENSOR_MAP_SWIZZLE_64B, CU_TENSOR_MAP_L2_PROMOTION_L2_128B, CU_TENSOR_MAP_FLOAT_OOB_FILL_NONE);
  }
  {
    cuuint64_t dims[3] = {64, 512, 8}, st[2] = {1024, 128};
    cuuint32_t box[3] = {64, 64, 2};
    enc(&mo, CU_TENSOR_MAP_DATA_TYPE_BFLOAT16, 3, d_in[3], dims, st, box, es, CU_TENSOR_MAP_INTERLEAVE_NONE,
        CU_TENSOR_MAP_SWIZZLE_128B, CU_TENSOR_MAP_L2_PROMOTION_L2_128B, CU_TENSOR_MAP_FLOAT_OOB_FILL_NONE);
  }
  {
    cuuint64_t dims[4] = {512, 4, 16, 32}, st[3] = {16384, 1024, 65536};
    cuuint32_t box[4] = {64, 4, 16, 2};
    enc(&mu, CU_TENSOR_MAP_DATA_TYPE_BFLOAT16, 4, d_in[4], dims, st, box, es, CU_TENSOR_MAP_INTERLEAVE_NONE,
        CU_TENSOR_MAP_SWIZZLE_128B, CU_TENSOR_MAP_L2_PROMOTION_L2_128B, CU_TENSOR_MAP_FLOAT_OOB_FILL_NONE);
  }
  {
    cuuint64_t dims[2] = {1024, 2048}, st[1] = {2048};
    cuuint32_t box[2] = {64, 16};
    enc(&mout, CU_TENSOR_MAP_DATA_TYPE_BFLOAT16, 2, d_out, dims, st, box, es, CU_TENSOR_MAP_INTERLEAVE_NONE,
        CU_TENSOR_MAP_SWIZZLE_128B, CU_TENSOR_MAP_L2_PROMOTION_NONE, CU_TENSOR_MAP_FLOAT_OOB_FILL_NONE);
  }
  Params P;
  P.x = (const __nv_bfloat16*)d_in[0];
  P.wphi = (const __nv_bfloat16*)d_in[2];
  P.wo = (const __nv_bfloat16*)d_in[3];
  P.logA = (const __nv_bfloat16*)d_in[5];
  P.Aim = (const __nv_bfloat16*)d_in[6];
  P.Cre = (const __nv_bfloat16*)d_in[7];
  P.Cim = (const __nv_bfloat16*)d_in[8];
  P.logdt = (const __nv_bfloat16*)d_in[9];
  P.Dskip = (const __nv_bfloat16*)d_in[10];
  P.out = (__nv_bfloat16*)d_out;
  cudaGetSymbolAddress((void**)&P.xs, g_x);
  P.ts = nullptr;
  cudaFuncSetAttribute(fused_kernel, cudaFuncAttributeMaxDynamicSharedMemorySize, SMEM_BYTES);
  fused_kernel<<<NCTA, NTHREADS, SMEM_BYTES>>>(P, mx, mw, mo, mu, mout);
}
```

```cpp
#include <cuda_runtime.h>
#include <cuda_bf16.h>
#include <cuda_fp16.h>
#include <cuda.h>
#include <stdint.h>

#define DBG_TS 0

namespace {

constexpr int NTHREADS = 512;
constexpr int NCTA = 128;
constexpr int OFF_W = 0;
constexpr int OFF_X = 98304;
constexpr int OFF_U = OFF_X + 65536;
constexpr int U_CH = 4416, U_ODD = 2240, U_PAD = 128;
constexpr int OFF_STG0 = OFF_U + 18432;
constexpr int SLAB = 3328;
constexpr int OFF_T = OFF_STG0 + 8 * SLAB;
constexpr int T_CH = 5216;
constexpr int T_D = 0;
constexpr int T_5 = 2144;
constexpr int T_3 = T_5 + 384;
constexpr int T_7 = T_5 + 1024;
constexpr int T_9 = T_7 + 320;
constexpr int T_KC = T_9 + 320;
constexpr int T_ST = T_5 - 1024;
constexpr int OFF_PHI = OFF_T + 4 * T_CH;
constexpr int OFF_EYE = OFF_PHI + 1024, OFF_ONE = OFF_EYE + 512;
constexpr int OFF_BAR = OFF_ONE + 256;
constexpr int SMEM_BYTES = OFF_BAR + 512 + 256 * DBG_TS;
constexpr uint32_t SB = 1024;
static_assert(T_KC + 2 * 656 <= T_CH, "table size");
static_assert(SMEM_BYTES <= 232448, "smem");
constexpr int MB_URAW = 0, MB_FULL = 1  , MB_WO = 17, MB_UFULL = 18, MB_O = 19  ,
              MB_EMPTY = 23  ;
__host__ __device__ constexpr uint32_t BAR(int i) { return SB + OFF_BAR + 8 * i; }
constexpr int NB_WG0 = 1, NB_ODONE = 2, NB_ST0 = 3  , NB_KV = 5, NB_YZ = 6, NB_INIT = 7, NB_PREP = 8, NB_PROD = 9, NB_KREAD = 10, NB_BDONE = 11, NB_GATE = 12,
              NB_Y = 7  ;
#define UAT 2
constexpr int U_AT = UAT;
constexpr int ZERO_STEP = 12;
constexpr int SPIN_MAX = 1 << 16;

constexpr int X_CNT = 0;
constexpr int X_PART = 256;
constexpr int X_O = X_PART + 16 * 8 * 144;
constexpr int X_Y = X_O + 32 * 32 * 128;
constexpr int X_UT = X_Y + 512 * 8 * 32;
constexpr int X_SIZE = X_UT + 512 * (U_CH / 16);
__device__ __align__(128) uint4 g_x[X_SIZE];
extern __shared__ uint8_t smem_raw[];
#define TS(i) do {} while (0)
#define TS1(i) do {} while (0)
#define GT(i) do {} while (0)
#define TSDUMP(base) do {} while (0)

__device__ __forceinline__ uint32_t smem_u32(const void* p) { return (uint32_t)__cvta_generic_to_shared(p); }
__device__ __forceinline__ void mbar_arrive(uint32_t b) {
  asm volatile("mbarrier.arrive.shared::cta.b64 _, [%0];" ::"r"(b) : "memory");
}
__device__ __forceinline__ void mbar_wait(uint32_t b) {
  uint32_t done = 0;
#pragma unroll 1
  for (int i = 0; i < SPIN_MAX && !done; i++) {
    asm volatile("{\n.reg .pred p;\nmbarrier.try_wait.parity.shared::cta.b64 p, [%1], 0, 4000;\nselp.u32 %0, 1, 0, p;\n}\n"
                 : "=r"(done) : "r"(b) : "memory");
  }
}
__device__ __forceinline__ void mbar_spin(uint32_t b) {
  uint32_t done = 0;
#pragma unroll 1
  for (int i = 0; i < (SPIN_MAX << 4) && !done; i++) {
    asm volatile("{\n.reg .pred p;\nmbarrier.try_wait.parity.shared::cta.b64 p, [%1], 0;\nselp.u32 %0, 1, 0, p;\n}\n"
                 : "=r"(done) : "r"(b) : "memory");
  }
}
__device__ __forceinline__ void mbar_init(uint32_t b, int n) {
  asm volatile("mbarrier.init.shared::cta.b64 [%0], %1;" ::"r"(b), "r"(n) : "memory");
}
__device__ __forceinline__ void mbar_expect(uint32_t b, int bytes) {
  asm volatile("mbarrier.arrive.expect_tx.shared::cta.b64 _, [%0], %1;" ::"r"(b), "r"(bytes) : "memory");
}
__device__ __forceinline__ void nb_sync(int id, int n) { asm volatile("bar.sync %0, %1;" ::"r"(id), "r"(n) : "memory"); }
__device__ __forceinline__ void nb_arrive(int id, int n) { asm volatile("bar.arrive %0, %1;" ::"r"(id), "r"(n) : "memory"); }
#define ELECT "{\n.reg .pred p;\nelect.sync _|p, 0xffffffff;\n@p "
__device__ __forceinline__ void e_arrive(uint32_t b) {
  asm volatile(ELECT "mbarrier.arrive.shared::cta.b64 _, [%0];\n}\n" ::"r"(b) : "memory");
}
__device__ __forceinline__ void e_expect(uint32_t b, int bytes) {
  asm volatile(ELECT "mbarrier.arrive.expect_tx.shared::cta.b64 _, [%0], %1;\n}\n" ::"r"(b), "r"(bytes) : "memory");
}
__device__ __forceinline__ void e_tma2d(uint32_t dst, const CUtensorMap* m, uint32_t bar, int c0, int c1) {
  asm volatile(ELECT "cp.async.bulk.tensor.2d.shared::cluster.global.mbarrier::complete_tx::bytes [%0], [%1, {%3,%4}], [%2];\n}\n"
               ::"r"(dst), "l"(m), "r"(bar), "r"(c0), "r"(c1) : "memory");
}
__device__ __forceinline__ void e_tma3d(uint32_t dst, const CUtensorMap* m, uint32_t bar, int c0, int c1, int c2) {
  asm volatile(ELECT "cp.async.bulk.tensor.3d.shared::cluster.global.mbarrier::complete_tx::bytes [%0], [%1, {%3,%4,%5}], [%2];\n}\n"
               ::"r"(dst), "l"(m), "r"(bar), "r"(c0), "r"(c1), "r"(c2) : "memory");
}
__device__ __forceinline__ void e_tma4d(uint32_t dst, const CUtensorMap* m, uint32_t bar, int c0, int c3) {
  asm volatile(ELECT "cp.async.bulk.tensor.4d.shared::cluster.global.mbarrier::complete_tx::bytes [%0], [%1, {%3,%5,%5,%4}], [%2];\n}\n"
               ::"r"(dst), "l"(m), "r"(bar), "r"(c0), "r"(c3), "r"(0) : "memory");
}
__device__ __forceinline__ void e_bulk(uint32_t dst, const void* src, int bytes, uint32_t bar) {
  asm volatile(ELECT "cp.async.bulk.shared::cluster.global.mbarrier::complete_tx::bytes [%0], [%1], %2, [%3];\n}\n"
               ::"r"(dst), "l"(src), "r"(bytes), "r"(bar) : "memory");
}
__device__ __forceinline__ void e_prefetch(const void* p, int bytes) {
  asm volatile(ELECT "cp.async.bulk.prefetch.L2.global [%0], %1;\n}\n" ::"l"(p), "r"(bytes) : "memory");
}
__device__ __forceinline__ void e_store2d(const CUtensorMap* m, uint32_t src, int c0, int c1) {
  asm volatile(ELECT "cp.async.bulk.tensor.2d.global.shared::cta.bulk_group [%0, {%2,%3}], [%1];\n}\n"
               ::"l"(m), "r"(src), "r"(c0), "r"(c1) : "memory");
}
__host__ __device__ constexpr uint64_t mkdesc(uint32_t addr, uint32_t lbo, uint32_t sbo, int swz) {
  return (uint64_t)((addr & 0x3FFFF) >> 4) | ((uint64_t)(lbo >> 4) << 16) | ((uint64_t)(sbo >> 4) << 32) |
         ((uint64_t)swz << 62);
}
#define SPLIT() asm volatile("{\n.reg .pred p;\nsetp.eq.u32 p, %0, %1;\n@p exit;\n}\n" ::"r"(blockIdx.y), "n"(__LINE__) : "memory")
#define SPLITN(n) asm volatile("{\n.reg .pred p;\nsetp.eq.u32 p, %0, %1;\n@p exit;\n}\n" ::"r"(blockIdx.y), "r"(4096 + (n)) : "memory")
#define WG_FENCE() asm volatile("wgmma.fence.sync.aligned;" ::: "memory")
#define WG_COMMIT() asm volatile("wgmma.commit_group.sync.aligned;" ::: "memory")
#define WG_WAIT(n) asm volatile("wgmma.wait_group.sync.aligned " #n ";" ::: "memory")

__device__ __forceinline__ void mma(float& d0, float& d1, float& d2, float& d3, uint32_t a0, uint32_t a1, uint32_t a2,
                                    uint32_t a3, uint32_t b0, uint32_t b1) {
  asm volatile("mma.sync.aligned.m16n8k16.row.col.f32.bf16.bf16.f32 {%0,%1,%2,%3},{%4,%5,%6,%7},{%8,%9},{%0,%1,%2,%3};"
               : "+f"(d0), "+f"(d1), "+f"(d2), "+f"(d3)
               : "r"(a0), "r"(a1), "r"(a2), "r"(a3), "r"(b0), "r"(b1));
}
__device__ __forceinline__ void mmac(float (&d)[4], uint32_t a0, uint32_t a1, uint32_t a2, uint32_t a3, uint32_t b0,
                                     uint32_t b1, const float (&c)[4]) {
  asm volatile("mma.sync.aligned.m16n8k16.row.col.f32.bf16.bf16.f32 {%0,%1,%2,%3},{%4,%5,%6,%7},{%8,%9},{%10,%11,%12,%13};"
               : "=f"(d[0]), "=f"(d[1]), "=f"(d[2]), "=f"(d[3])
               : "r"(a0), "r"(a1), "r"(a2), "r"(a3), "r"(b0), "r"(b1), "f"(c[0]), "f"(c[1]), "f"(c[2]), "f"(c[3]));
}
__device__ __forceinline__ void mma_p(int p, float (&d)[4], uint32_t a0, uint32_t a1, uint32_t a2, uint32_t a3, uint32_t b0, uint32_t b1) {
  asm volatile("{\n.reg .pred q;\nsetp.ne.b32 q, %10, 0;\n"
               "@q mma.sync.aligned.m16n8k16.row.col.f32.bf16.bf16.f32 {%0,%1,%2,%3},{%4,%5,%6,%7},{%8,%9},{%0,%1,%2,%3};\n}\n"
               : "+f"(d[0]), "+f"(d[1]), "+f"(d[2]), "+f"(d[3])
               : "r"(a0), "r"(a1), "r"(a2), "r"(a3), "r"(b0), "r"(b1), "r"(p));
}
__device__ __forceinline__ void mmac_p(int p, float (&d)[4], uint32_t a0, uint32_t a1, uint32_t a2, uint32_t a3, uint32_t b0,
                                       uint32_t b1, const float (&c)[4]) {
  asm volatile("{\n.reg .pred q;\nsetp.ne.b32 q, %14, 0;\n"
               "@q mma.sync.aligned.m16n8k16.row.col.f32.bf16.bf16.f32 {%0,%1,%2,%3},{%4,%5,%6,%7},{%8,%9},{%10,%11,%12,%13};\n}\n"
               : "+f"(d[0]), "+f"(d[1]), "+f"(d[2]), "+f"(d[3])
               : "r"(a0), "r"(a1), "r"(a2), "r"(a3), "r"(b0), "r"(b1), "f"(c[0]), "f"(c[1]), "f"(c[2]), "f"(c[3]), "r"(p));
}
__device__ __forceinline__ void mma_h(float (&d)[4], const uint32_t (&a)[4], uint32_t b0, uint32_t b1) {
  asm volatile("mma.sync.aligned.m16n8k16.row.col.f32.f16.f16.f32 {%0,%1,%2,%3},{%4,%5,%6,%7},{%8,%9},{%0,%1,%2,%3};"
               : "+f"(d[0]), "+f"(d[1]), "+f"(d[2]), "+f"(d[3]) : "r"(a[0]), "r"(a[1]), "r"(a[2]), "r"(a[3]), "r"(b0), "r"(b1));
}
__device__ __forceinline__ void mma0(float& d0, float& d1, float& d2, float& d3, uint32_t a0, uint32_t a1, uint32_t a2,
                                     uint32_t a3, uint32_t b0, uint32_t b1) {
  asm volatile("mma.sync.aligned.m16n8k16.row.col.f32.bf16.bf16.f32 {%0,%1,%2,%3},{%4,%5,%6,%7},{%8,%9},{%10,%10,%10,%10};"
               : "=f"(d0), "=f"(d1), "=f"(d2), "=f"(d3)
               : "r"(a0), "r"(a1), "r"(a2), "r"(a3), "r"(b0), "r"(b1), "f"(0.f));
}
__device__ __forceinline__ uint32_t pack_bf(float lo, float hi) {
  uint32_t r;
  asm("cvt.rn.bf16x2.f32 %0, %1, %2;" : "=r"(r) : "f"(hi), "f"(lo));
  return r;
}
__device__ __forceinline__ float bf_lo(uint32_t w) { return __uint_as_float(w << 16); }
__device__ __forceinline__ float bf_hi(uint32_t w) { return __uint_as_float(w & 0xffff0000u); }
__device__ __forceinline__ float bf_round(float x) { return __bfloat162float(__float2bfloat16_rn(x)); }
__device__ __forceinline__ uint32_t bmax2(uint32_t a, uint32_t b) {
  uint32_t r; asm("max.bf16x2 %0, %1, %2;" : "=r"(r) : "r"(a), "r"(b)); return r;
}
__device__ __forceinline__ uint32_t bmin2(uint32_t a, uint32_t b) {
  uint32_t r; asm("min.bf16x2 %0, %1, %2;" : "=r"(r) : "r"(a), "r"(b)); return r;
}
__device__ __forceinline__ float ex2(float x) { float r; asm("ex2.approx.ftz.f32 %0, %1;" : "=f"(r) : "f"(x)); return r; }
__device__ __forceinline__ float rcp(float x) { float r; asm("rcp.approx.ftz.f32 %0, %1;" : "=f"(r) : "f"(x)); return r; }
__device__ __forceinline__ void ldsm4(uint32_t (&r)[4], uint32_t a) {
  asm volatile("ldmatrix.sync.aligned.m8n8.x4.shared.b16 {%0,%1,%2,%3}, [%4];"
               : "=r"(r[0]), "=r"(r[1]), "=r"(r[2]), "=r"(r[3]) : "r"(a) : "memory");
}
__device__ __forceinline__ void ldsm4t(uint32_t (&r)[4], uint32_t a) {
  asm volatile("ldmatrix.sync.aligned.m8n8.x4.trans.shared.b16 {%0,%1,%2,%3}, [%4];"
               : "=r"(r[0]), "=r"(r[1]), "=r"(r[2]), "=r"(r[3]) : "r"(a) : "memory");
}
__device__ __forceinline__ void stsm4(uint32_t a, uint32_t r0, uint32_t r1, uint32_t r2, uint32_t r3) {
  asm volatile("stmatrix.sync.aligned.m8n8.x4.shared.b16 [%0], {%1,%2,%3,%4};"
               ::"r"(a), "r"(r0), "r"(r1), "r"(r2), "r"(r3) : "memory");
}
__device__ __forceinline__ uint32_t lds32(uint32_t a) {
  uint32_t r; asm volatile("ld.shared.u32 %0, [%1];" : "=r"(r) : "r"(a) : "memory"); return r;
}
__device__ __forceinline__ uint32_t lds16(uint32_t a) {
  uint32_t r; asm volatile("{\n.reg .u16 h;\nld.shared.u16 h, [%1];\ncvt.u32.u16 %0, h;\n}\n" : "=r"(r) : "r"(a) : "memory"); return r;
}
__device__ __forceinline__ uint2 lds64(uint32_t a) {
  uint2 r; asm volatile("ld.shared.v2.u32 {%0,%1}, [%2];" : "=r"(r.x), "=r"(r.y) : "r"(a) : "memory"); return r;
}
__device__ __forceinline__ uint4 lds128(uint32_t a) {
  uint4 r;
  asm volatile("ld.shared.v4.u32 {%0,%1,%2,%3}, [%4];" : "=r"(r.x), "=r"(r.y), "=r"(r.z), "=r"(r.w) : "r"(a) : "memory");
  return r;
}
__device__ __forceinline__ void sts32(uint32_t a, uint32_t v) { asm volatile("st.shared.u32 [%0], %1;" ::"r"(a), "r"(v) : "memory"); }
__device__ __forceinline__ void sts16(uint32_t a, uint32_t v) {
  asm volatile("{\n.reg .u16 h;\ncvt.u16.u32 h, %1;\nst.shared.u16 [%0], h;\n}\n" ::"r"(a), "r"(v) : "memory");
}
__device__ __forceinline__ void sts64(uint32_t a, uint32_t x, uint32_t y) {
  asm volatile("st.shared.v2.u32 [%0], {%1,%2};" ::"r"(a), "r"(x), "r"(y) : "memory");
}
__device__ __forceinline__ void sts128(uint32_t a, uint32_t x, uint32_t y, uint32_t z, uint32_t w) {
  asm volatile("st.shared.v4.u32 [%0], {%1,%2,%3,%4};" ::"r"(a), "r"(x), "r"(y), "r"(z), "r"(w) : "memory");
}
__device__ __forceinline__ uint4 ld_x(const uint4* p) {
  uint4 r;
  asm volatile("{\n.reg .b128 t;\nld.relaxed.gpu.global.b128 t, [%4];\nmov.b128 {%0,%1,%2,%3}, t;\n}\n"
               : "=r"(r.x), "=r"(r.y), "=r"(r.z), "=r"(r.w) : "l"(p) : "memory");
  return r;
}
__device__ __forceinline__ uint32_t ld_x32(const uint32_t* p) {
  uint32_t r; asm volatile("ld.relaxed.gpu.global.u32 %0, [%1];" : "=r"(r) : "l"(p) : "memory"); return r;
}
__device__ __forceinline__ void st_x(uint4* p, uint32_t x, uint32_t y, uint32_t z, uint32_t w) {
  asm volatile("{\n.reg .b128 t;\nmov.b128 t, {%1,%2,%3,%4};\nst.relaxed.gpu.global.b128 [%0], t;\n}\n"
               ::"l"(p), "r"(x), "r"(y), "r"(z), "r"(w) : "memory");
}
__device__ __forceinline__ void st_x_p(int p, uint4* a, uint32_t x, uint32_t y, uint32_t z, uint32_t w) {
  asm volatile("{\n.reg .b128 t;\n.reg .pred q;\nsetp.ne.b32 q, %5, 0;\nmov.b128 t, {%1,%2,%3,%4};\n@q st.relaxed.gpu.global.b128 [%0], t;\n}\n"
               ::"l"(a), "r"(x), "r"(y), "r"(z), "r"(w), "r"(p) : "memory");
}
__device__ __forceinline__ void sts64_p(int p, uint32_t a, uint32_t x, uint32_t y) {
  asm volatile("{\n.reg .pred q;\nsetp.ne.b32 q, %3, 0;\n@q st.shared.v2.u32 [%0], {%1,%2};\n}\n" ::"r"(a), "r"(x), "r"(y), "r"(p) : "memory");
}
__device__ __forceinline__ void st_x32(uint32_t* p, uint32_t x) {
  asm volatile("st.relaxed.gpu.global.u32 [%0], %1;" ::"l"(p), "r"(x) : "memory");
}
__device__ __forceinline__ uint32_t nz(uint32_t w) { return max(w, 1u); }
__device__ __forceinline__ uint32_t fu(float x) { return __float_as_uint(x); }
__device__ __forceinline__ float uf(uint32_t x) { return __uint_as_float(x); }

__device__ __forceinline__ void wgmma_ss_n96(float (&d)[48], uint64_t da, uint64_t db, int sc) {
  asm volatile("{\n.reg .pred p;\nsetp.ne.b32 p, %50, 0;\n"
      "wgmma.mma_async.sync.aligned.m64n96k16.f32.bf16.bf16 "
      "{%0,%1,%2,%3,%4,%5,%6,%7,%8,%9,%10,%11,%12,%13,%14,%15,%16,%17,%18,%19,%20,%21,%22,%23,%24,%25,%26,%27,%28,%29,%30,%31,%32,%33,%34,%35,%36,%37,%38,%39,%40,%41,%42,%43,%44,%45,%46,%47}, "
      "%48, %49, p, 1, 1, 0, 1;\n}\n"
      : "+f"(d[0]), "+f"(d[1]), "+f"(d[2]), "+f"(d[3]), "+f"(d[4]), "+f"(d[5]), "+f"(d[6]), "+f"(d[7]),
        "+f"(d[8]), "+f"(d[9]), "+f"(d[10]), "+f"(d[11]), "+f"(d[12]), "+f"(d[13]), "+f"(d[14]), "+f"(d[15]),
        "+f"(d[16]), "+f"(d[17]), "+f"(d[18]), "+f"(d[19]), "+f"(d[20]), "+f"(d[21]), "+f"(d[22]), "+f"(d[23]),
        "+f"(d[24]), "+f"(d[25]), "+f"(d[26]), "+f"(d[27]), "+f"(d[28]), "+f"(d[29]), "+f"(d[30]), "+f"(d[31]),
        "+f"(d[32]), "+f"(d[33]), "+f"(d[34]), "+f"(d[35]), "+f"(d[36]), "+f"(d[37]), "+f"(d[38]), "+f"(d[39]),
        "+f"(d[40]), "+f"(d[41]), "+f"(d[42]), "+f"(d[43]), "+f"(d[44]), "+f"(d[45]), "+f"(d[46]), "+f"(d[47])
      : "l"(da), "l"(db), "r"(sc));
}

__device__ __forceinline__ void wgmma_ss_n128(float (&d)[64], uint64_t da, uint64_t db, int sc) {
  asm volatile("{\n.reg .pred p;\nsetp.ne.b32 p, %66, 0;\n"
      "wgmma.mma_async.sync.aligned.m64n128k16.f32.bf16.bf16 "
      "{%0,%1,%2,%3,%4,%5,%6,%7,%8,%9,%10,%11,%12,%13,%14,%15,%16,%17,%18,%19,%20,%21,%22,%23,%24,%25,%26,%27,%28,%29,%30,%31,%32,%33,%34,%35,%36,%37,%38,%39,%40,%41,%42,%43,%44,%45,%46,%47,%48,%49,%50,%51,%52,%53,%54,%55,%56,%57,%58,%59,%60,%61,%62,%63}, "
      "%64, %65, p, 1, 1, 0, 1;\n}\n"
      : "+f"(d[0]), "+f"(d[1]), "+f"(d[2]), "+f"(d[3]), "+f"(d[4]), "+f"(d[5]), "+f"(d[6]), "+f"(d[7]),
        "+f"(d[8]), "+f"(d[9]), "+f"(d[10]), "+f"(d[11]), "+f"(d[12]), "+f"(d[13]), "+f"(d[14]), "+f"(d[15]),
        "+f"(d[16]), "+f"(d[17]), "+f"(d[18]), "+f"(d[19]), "+f"(d[20]), "+f"(d[21]), "+f"(d[22]), "+f"(d[23]),
        "+f"(d[24]), "+f"(d[25]), "+f"(d[26]), "+f"(d[27]), "+f"(d[28]), "+f"(d[29]), "+f"(d[30]), "+f"(d[31]),
        "+f"(d[32]), "+f"(d[33]), "+f"(d[34]), "+f"(d[35]), "+f"(d[36]), "+f"(d[37]), "+f"(d[38]), "+f"(d[39]),
        "+f"(d[40]), "+f"(d[41]), "+f"(d[42]), "+f"(d[43]), "+f"(d[44]), "+f"(d[45]), "+f"(d[46]), "+f"(d[47]),
        "+f"(d[48]), "+f"(d[49]), "+f"(d[50]), "+f"(d[51]), "+f"(d[52]), "+f"(d[53]), "+f"(d[54]), "+f"(d[55]),
        "+f"(d[56]), "+f"(d[57]), "+f"(d[58]), "+f"(d[59]), "+f"(d[60]), "+f"(d[61]), "+f"(d[62]), "+f"(d[63])
      : "l"(da), "l"(db), "r"(sc));
}

__device__ __forceinline__ void wgmma_ss_n40(float (&d)[20], uint64_t da, uint64_t db, int sc) {
  asm volatile("{\n.reg .pred p;\nsetp.ne.b32 p, %22, 0;\n"
      "wgmma.mma_async.sync.aligned.m64n40k16.f32.bf16.bf16 "
      "{%0,%1,%2,%3,%4,%5,%6,%7,%8,%9,%10,%11,%12,%13,%14,%15,%16,%17,%18,%19}, "
      "%20, %21, p, 1, 1, 1, 1;\n}\n"
      : "+f"(d[0]), "+f"(d[1]), "+f"(d[2]), "+f"(d[3]), "+f"(d[4]), "+f"(d[5]), "+f"(d[6]), "+f"(d[7]),
        "+f"(d[8]), "+f"(d[9]), "+f"(d[10]), "+f"(d[11]), "+f"(d[12]), "+f"(d[13]), "+f"(d[14]), "+f"(d[15]),
        "+f"(d[16]), "+f"(d[17]), "+f"(d[18]), "+f"(d[19])
      : "l"(da), "l"(db), "r"(sc));
}

__device__ __forceinline__ void wgmma_rs_n8(float (&d)[4], const uint4& a, uint64_t db, int sc) {
  asm volatile("{\n.reg .pred p;\nsetp.ne.b32 p, %9, 0;\n"
      "wgmma.mma_async.sync.aligned.m64n8k16.f32.bf16.bf16 "
      "{%0,%1,%2,%3}, "
      "{%4,%5,%6,%7}, %8, p, 1, 1, 1;\n}\n"
      : "+f"(d[0]), "+f"(d[1]), "+f"(d[2]), "+f"(d[3])
      : "r"(a.x), "r"(a.y), "r"(a.z), "r"(a.w), "l"(db), "r"(sc));
}

__device__ __forceinline__ void wgmma_rs_n16(float (&d)[8], const uint4& a, uint64_t db, int sc) {
  asm volatile("{\n.reg .pred p;\nsetp.ne.b32 p, %13, 0;\n"
      "wgmma.mma_async.sync.aligned.m64n16k16.f32.bf16.bf16 "
      "{%0,%1,%2,%3,%4,%5,%6,%7}, "
      "{%8,%9,%10,%11}, %12, p, 1, 1, 1;\n}\n"
      : "+f"(d[0]), "+f"(d[1]), "+f"(d[2]), "+f"(d[3]), "+f"(d[4]), "+f"(d[5]), "+f"(d[6]), "+f"(d[7])
      : "r"(a.x), "r"(a.y), "r"(a.z), "r"(a.w), "l"(db), "r"(sc));
}

__device__ __forceinline__ void wgmma_rs_n24(float (&d)[12], const uint4& a, uint64_t db, int sc) {
  asm volatile("{\n.reg .pred p;\nsetp.ne.b32 p, %17, 0;\n"
      "wgmma.mma_async.sync.aligned.m64n24k16.f32.bf16.bf16 "
      "{%0,%1,%2,%3,%4,%5,%6,%7,%8,%9,%10,%11}, "
      "{%12,%13,%14,%15}, %16, p, 1, 1, 1;\n}\n"
      : "+f"(d[0]), "+f"(d[1]), "+f"(d[2]), "+f"(d[3]), "+f"(d[4]), "+f"(d[5]), "+f"(d[6]), "+f"(d[7]),
        "+f"(d[8]), "+f"(d[9]), "+f"(d[10]), "+f"(d[11])
      : "r"(a.x), "r"(a.y), "r"(a.z), "r"(a.w), "l"(db), "r"(sc));
}

struct Params {
  const __nv_bfloat16 *logA, *Aim, *Cre, *Cim, *logdt, *Dskip, *x, *wphi, *wo;
  __nv_bfloat16* out;
  uint4* xs;
  long long* ts;
};

__device__ __forceinline__ uint4 tr_row(const uint4 (&v)[8], int i) {
  uint32_t o[4];
#pragma unroll
  for (int m = 0; m < 4; m++) {
    const uint4 &ra = v[2 * m], &rb = v[2 * m + 1];
    const int k = i >> 1;
    const uint32_t xa = k == 0 ? ra.x : k == 1 ? ra.y : k == 2 ? ra.z : ra.w;
    const uint32_t xb = k == 0 ? rb.x : k == 1 ? rb.y : k == 2 ? rb.z : rb.w;
    o[m] = __byte_perm(xa, xb, (i & 1) ? 0x7632 : 0x5410);
  }
  return make_uint4(o[0], o[1], o[2], o[3]);
}

struct cpx { float r, i; };
__device__ __forceinline__ cpx csq(cpx a) { return {a.r * a.r - a.i * a.i, 2.f * (a.r * a.i)}; }
__device__ __forceinline__ cpx polar(float e, float t) {
  const float m = ex2(e);
  return {m * __cosf(t), m * __sinf(t)};
}

struct KgenRaw { uint32_t la, ai, cr, ci, ldt; };
__device__ __forceinline__ KgenRaw kgen_load(const Params& P, int d, int unit, int lane, int on) {
  const int o = d * 64 + unit * 32 + lane;
  KgenRaw r = {0, 0, 0, 0, 0};
  asm volatile("{\n.reg .pred p;\nsetp.ne.b32 p, %10, 0;\n@p ld.global.nc.u32 %0, [%5];\n@p ld.global.nc.u32 %1, [%6];\n"
               "@p ld.global.nc.u32 %2, [%7];\n@p ld.global.nc.u32 %3, [%8];\n@p ld.global.nc.u16 %4, [%9];\n}\n"
               : "+r"(r.la), "+r"(r.ai), "+r"(r.cr), "+r"(r.ci), "+r"(r.ldt)
               : "l"((const uint32_t*)P.logA + o), "l"((const uint32_t*)P.Aim + o), "l"((const uint32_t*)P.Cre + o),
                 "l"((const uint32_t*)P.Cim + o), "l"(P.logdt + d), "r"(on));
  return r;
}
struct hc { __half2 r, i; };
struct cpx2 { cpx a, b; };
__device__ __forceinline__ cpx2 csq2(const cpx2& v) { return {csq(v.a), csq(v.b)}; }
__device__ __forceinline__ hc toh(const cpx2& v) { return {__floats2half2_rn(v.a.r, v.b.r), __floats2half2_rn(v.a.i, v.b.i)}; }
__device__ __forceinline__ hc hmul(const hc& z, const hc& w) {
  return {__hfma2(z.r, w.r, __hneg2(__hmul2(z.i, w.i))), __hfma2(z.r, w.i, __hmul2(z.i, w.r))};
}
__device__ __forceinline__ hc hmulc(const hc& z, const hc& w) {
  return {__hfma2(z.r, w.r, __hmul2(z.i, w.i)), __hfma2(z.i, w.r, __hneg2(__hmul2(z.r, w.i)))};
}
__device__ __forceinline__ uint32_t hu(__half2 v) { return *(const uint32_t*)&v; }
__device__ __forceinline__ __half2 uh(uint32_t v) { return *(const __half2*)&v; }

struct KgenAddr { uint32_t sa, lb, lm[4]; };
__device__ __forceinline__ KgenAddr kgen_addr(int lane, uint32_t buf) {
  KgenAddr a;
  a.sa = buf + (lane & 7) * 128 + ((((lane >> 3) ^ lane) & 7) << 4);
  const int q = lane >> 4;
  const uint32_t b = buf + ((lane >> 3) & 1) * 1024 + q * 128;
  a.lb = b + (((lane ^ q) & 7) << 4);
  a.lm[0] = b + (q << 4);
  a.lm[1] = b + ((1 ^ q) << 4);
  a.lm[2] = b + (((2 + (lane & 1)) ^ q) << 4);
  a.lm[3] = b + (((4 + (lane & 3)) ^ q) << 4);
  asm volatile("" : "+r"(a.sa), "+r"(a.lb), "+r"(a.lm[0]), "+r"(a.lm[1]), "+r"(a.lm[2]), "+r"(a.lm[3]));
  return a;
}
__device__ __forceinline__ void kgen_unit(const KgenRaw& r, const KgenAddr& ad, uint32_t zero, float (&k)[5][4], float& k2048, float& sc) {
  const float dt = bf_round(expf(bf_lo(r.ldt)));
  const uint32_t ar = pack_bf(ex2(bf_lo(r.la) * 1.4426950408889634f), ex2(bf_hi(r.la) * 1.4426950408889634f));
  const float ca = dt * -1.4426950408889634f, a0 = bf_lo(ar) * ca, a1 = bf_hi(ar) * ca;
  const float f0 = bf_lo(r.ai) * dt, f1 = bf_hi(r.ai) * dt;
  const float r0 = f0 * 20.21267777267071f, r1 = f1 * 20.21267777267071f;
  const uint32_t cm = __vmaxu2(r.cr & 0x7fff7fffu, r.ci & 0x7fff7fffu);
  const uint32_t ex = min(max(__reduce_max_sync(0xffffffffu, max(cm >> 16, cm & 0xffffu)) >> 7, 1u), 253u);
  const float cs = uf((254u - ex) << 23);
  sc = 2.f * dt * uf(ex << 23);
  const cpx2 C = {{bf_lo(r.cr) * cs, bf_lo(r.ci) * -cs}, {bf_hi(r.cr) * cs, bf_hi(r.ci) * -cs}};
  auto put = [&](const hc (&v)[8]) {
    stsm4(ad.sa, hu(v[0].r), hu(v[1].r), hu(v[2].r), hu(v[3].r));
    stsm4(ad.sa + 1024, hu(v[0].i), hu(v[1].i), hu(v[2].i), hu(v[3].i));
    stsm4(ad.sa ^ 64, hu(v[4].r), hu(v[5].r), hu(v[6].r), hu(v[7].r));
    stsm4((ad.sa ^ 64) + 1024, hu(v[4].i), hu(v[5].i), hu(v[6].i), hu(v[7].i));
    __syncwarp();
  };
  auto get = [&](uint32_t (&o)[4][4], uint32_t a) {
#pragma unroll
    for (int i = 0; i < 4; i++) ldsm4(o[i], (a ^ (i << 5)) + i * 256);
  };
  auto at = [](const uint32_t (&o)[4][4], int s) { return hc{uh(o[s >> 1][2 * (s & 1)]), uh(o[s >> 1][2 * (s & 1) + 1])}; };
  uint32_t A[8][4];
  auto tile = [&](int j, const uint32_t (&B)[4][4]) {
    k[j][0] = k[j][1] = k[j][2] = k[j][3] = 0.f;
#pragma unroll
    for (int s = 0; s < 8; s++) mma_h(k[j], A[s], B[s >> 1][2 * (s & 1)], B[s >> 1][2 * (s & 1) + 1]);
  };
  const cpx2 w1 = {polar(a0, f0), polar(a1, f1)};
  const cpx2 w127 = {polar(a0 * 127.f, (r0 - rintf(r0)) * 6.283185307179586f), polar(a1 * 127.f, (r1 - rintf(r1)) * 6.283185307179586f)};
  const cpx2 w2 = csq2(w1), w4 = csq2(w2);
  uint32_t T0[4][4], X[4][4], M[3][4][4];
  {
    hc t[8];
    t[0] = {uh(0x3C003C00u), uh(0u)}; t[1] = toh(w1); t[2] = toh(w2); t[4] = toh(w4);
    t[3] = hmul(t[1], t[2]); t[5] = hmul(t[1], t[4]); t[6] = hmul(t[2], t[4]); t[7] = hmul(t[3], t[4]);
    put(t); get(T0, ad.lb);
  }
  const cpx2 w8 = csq2(w4), w16 = csq2(w8), w32 = csq2(w16), w64 = csq2(w32);
  {
    const hc m8 = toh(w8), m16 = toh(w16), m32 = toh(w32);
    hc a[8];
    a[0] = toh(C); a[1] = hmulc(a[0], m8);
    a[2] = hmulc(a[0], m16); a[3] = hmulc(a[1], m16);
#pragma unroll
    for (int i = 0; i < 4; i++) a[4 + i] = hmulc(a[i], m32);
    put(a); get(X, ad.lb);
  }
    const cpx2 w128 = {{w127.a.r * w1.a.r - w127.a.i * w1.a.i, w127.a.r * w1.a.i + w127.a.i * w1.a.r},
                     {w127.b.r * w1.b.r - w127.b.i * w1.b.i, w127.b.r * w1.b.i + w127.b.i * w1.b.r}};
  const cpx2 w256 = csq2(w128), w512 = csq2(w256);
  const hc m128 = toh(w128), m256 = toh(w256), m512 = toh(w512);
  {
    const hc m254 = toh(csq2(w127)), m127 = toh(w127);
    hc m[8];
    m[0] = toh(w64); m[1] = m128; m[2] = m256; m[3] = hmul(m127, m256);
    m[4] = m512; m[5] = hmul(m127, m512); m[6] = hmul(m[4], m254); m[7] = hmul(m[5], m254);
    put(m);
    get(M[0], ad.lm[0]);
#pragma unroll
    for (int s = 0; s < 8; s++) {
      const hc z = at(X, s), y = hmulc(z, at(M[0], s));
      A[s][0] = hu(z.r) + zero; A[s][1] = hu(y.r); A[s][2] = hu(z.i) + zero; A[s][3] = hu(y.i);
    }
#pragma unroll
    for (int i = 0; i < 3; i++) get(M[i], ad.lm[i + 1]);
  }
  tile(0, T0);
  const cpx2 w1024 = csq2(w512), we = csq2(w1024);
  {
    hc t[8];
    t[0] = toh(w1024); t[1] = hmul(t[0], m128);
    t[2] = hmul(t[0], m256); t[3] = hmul(t[1], m256);
#pragma unroll
    for (int i = 0; i < 4; i++) t[4 + i] = hmul(t[i], m512);
    put(t); get(X, ad.lb);
  }
  k2048 = (C.a.r * we.a.r + C.a.i * we.a.i + C.b.r * we.b.r + C.b.i * we.b.i) * sc;
#pragma unroll
  for (int j = 1; j < 5; j++) k[j][0] = k[j][1] = k[j][2] = k[j][3] = 0.f;
#pragma unroll
  for (int s = 0; s < 8; s++) {
#pragma unroll
    for (int j = 0; j < 3; j++) {
      const hc y = hmul(at(T0, s), at(M[j], s));
      mma_h(k[1 + j], A[s], hu(y.r), hu(y.i));
    }
    mma_h(k[4], A[s], X[s >> 1][2 * (s & 1)], X[s >> 1][2 * (s & 1) + 1]);
  }
}

__device__ __forceinline__ void build_tables(uint32_t tb, int lane, float (&k)[5][4], float k2048) {
  const int g = lane >> 2, c = lane & 3;
  const uint32_t kc = tb + T_KC + 16;
  {
    const uint32_t a0 = kc + 16 * g + 4 * c, a2 = kc + 2 * (256 + 4 * g + c);
    const uint32_t a3 = kc + 2 * (384 + 2 * g + 64 * (c & 1) + (c >> 1)), a4 = kc + 2 * (512 + g + 32 * c);
#pragma unroll
    for (int r = 0; r < 2; r++) {
      sts32(a0 + 128 * r, pack_bf(k[0][2 * r], k[0][2 * r + 1]));
      sts32(a0 + 128 * r + 256, pack_bf(k[1][2 * r], k[1][2 * r + 1]));
      const uint32_t w2 = pack_bf(k[2][2 * r], k[2][2 * r + 1]);
      const uint32_t w3 = pack_bf(k[3][2 * r], k[3][2 * r + 1]);
      const uint32_t w4 = pack_bf(k[4][2 * r], k[4][2 * r + 1]);
      sts16(a2 + 64 * r, w2); sts16(a2 + 64 * r + 128, w2 >> 16);
      sts16(a3 + 32 * r, w3); sts16(a3 + 32 * r + 64, w3 >> 16);
      sts16(a4 + 16 * r, w4); sts16(a4 + 16 * r + 32, w4 >> 16);
    }
  }
  if (lane == 0) { sts16(kc + 2 * 640, pack_bf(k2048, 0.f)); sts32(kc - 4, 0); }
  __syncwarp();
  const uint32_t td = tb + T_D + 32;
#pragma unroll
  for (int hf = 0; hf < 2; hf++) {
    const uint2 v = lds64(kc + 256 * hf + 8 * lane);
    const uint32_t pv = lds32(kc + 256 * hf + 8 * lane - 4);
    sts128(td + 512 * hf + 16 * lane, __byte_perm(v.x, pv, 0x7610), __byte_perm(v.x, v.x, 0x1032), __byte_perm(v.y, v.x, 0x7610),
           __byte_perm(v.y, v.y, 0x1032));
  }
#pragma unroll
  for (int hf = 0; hf < 2; hf++) {
    const uint32_t v = lds32(kc + 512 + 128 * hf + 4 * lane), nx = lds32(kc + 516 + 128 * hf + 4 * lane);
    uint32_t w0 = __byte_perm(v, v, 0x1010);
    const uint32_t w1 = w0;
    if (hf == 0) { const uint32_t pv = lds32(kc + 508); if (lane == 0) w0 = __byte_perm(v, pv, 0x7610); }
    sts128(td + 1024 + 512 * hf + 16 * lane, w0, w1, __byte_perm(v, v, 0x1032), __byte_perm(nx, v, 0x7610));
  }
  {
    const uint32_t kk = lds16(kc + 2 * 384);
    const uint32_t w = lane < 3 ? (kk | (kk << 16)) : (lane == 3 ? (kk << 16) : 0u);
    if (lane < 24) sts32(td + 4 * (lane < 16 ? 512 + lane : lane - 24), w);
    const uint32_t lo_ = lds16(kc + 2 * 511), le_ = lds16(kc + 2 * 512);
    const uint32_t ja = tb + T_5 + (lane < 16 ? 4 * lane : 256 + 4 * lane);
    sts32(ja, lane == 16 ? (le_ << 16) : 0u);
    sts32(ja + 384, lane == 16 ? (lo_ << 16) : 0u);
    sts32(tb + (lane < 16 ? T_7 : T_9 - 64) + 4 * lane, 0u);
  }
#pragma unroll
  for (int s = 0; s < 2; s++) {
    const uint32_t b = kc + 2 * (s ? 512 : 384) + 8 * lane;
    const uint2 v = lds64(b);
    uint32_t em = lds16(b - 2), e0 = v.x;
    const uint32_t e4 = lds16(b + 8);
    if (lane == 0) { em = 0; e0 = 0; }
    sts64(tb + (s ? T_7 : T_3) + 64 + 8 * lane, __byte_perm(v.x, em, 0x5432), __byte_perm(v.y, v.x, 0x7632));
    sts64(tb + (s ? T_9 : T_5) + 64 + 8 * lane, __byte_perm(v.y, e0, 0x5410), __byte_perm(e4, v.y, 0x5410));
  }
  __syncwarp();
}

__device__ __forceinline__ uint32_t box2w(int lo, int n, int o) {
  return ((unsigned)(o - lo) < (unsigned)n ? 0x3F80u : 0u) | ((unsigned)(o + 1 - lo) < (unsigned)n ? 0x3F800000u : 0u);
}

__device__ __forceinline__ void conv_channel(uint32_t ub, uint32_t tb, int lane, uint4* ydst) {
  const int g = lane >> 2, c = lane & 3, x = g - 2 * c;
  const int mi = lane >> 3;
  const uint32_t qa = ub + U_PAD + 16 * (lane & 7) + ((mi == 0 || mi == 3) ? U_ODD : 0) - (mi == 0 ? 16 : 0);
  const uint32_t hb = ub + U_PAD + (mi & 1) * U_ODD + 16 * ((lane >> 4) + (lane & 7)) - 16;
  const uint32_t kv = lds16(tb + T_KC + 16 + 2 * 512);
  const int oh = c < 2 ? 8 + 2 * c : 2 * c - 8, og = c < 3 ? 2 * c : -10;
  uint32_t bx[4] = {box2w(g - 4, 9, 2 * c), box2w(g - 3, 7, 2 * c), box2w(g - 4, 9, oh), box2w(g - 3, 7, oh)};
  uint32_t by[4] = {box2w(g - 10, 5, 2 * c - 8), box2w(g - 5, 3, 2 * c - 8), box2w(g - 10, 5, og), box2w(g - 5, 3, og)};
  uint32_t lb0 = ((unsigned)(x + 5) < 2u ? kv : 0u) | ((unsigned)(x + 4) < 2u ? kv << 16 : 0u);
  uint32_t lb1 = ((unsigned)(x - 3) < 2u ? kv : 0u) | ((unsigned)(x - 4) < 2u ? kv << 16 : 0u);
  const int q0 = g - 1, q1 = c < 3 ? g : g - 2;
  uint32_t y0a = ub + U_PAD + (q0 & 1) * U_ODD + 16 * (q0 >> 1) + 4 * c;
  uint32_t y1a = ub + U_PAD + (q1 & 1) * U_ODD + 16 * (q1 >> 1) + 4 * c;
#pragma unroll
  for (int i = 0; i < 4; i++) asm volatile("" : "+r"(bx[i]), "+r"(by[i]));
  asm volatile("" : "+r"(lb0), "+r"(lb1), "+r"(y0a), "+r"(y1a));
  mbar_wait(BAR(MB_UFULL));
  mbar_spin(BAR(MB_EMPTY + 15));
  TS(36);
  float acc[16][4];
  {
    uint32_t z09[8], z07[8], zm9[8], zm7[8];
#pragma unroll
    for (int i = 0; i < 8; i++) {
      uint32_t h[4];
      ldsm4(h, hb + 128 * i);
      float y0, y1, y2, y3, w0, w1, w2, w3;
      mma0(y0, y1, y2, y3, bx[0], bx[1], bx[2], bx[3], h[2], c < 2 ? h[3] : h[1]);
      mma0(w0, w1, w2, w3, bx[0], bx[1], bx[2], bx[3], h[1], c < 2 ? h[2] : h[0]);
      z09[i] = pack_bf(y0, y1); z07[i] = pack_bf(y2, y3);
      zm9[i] = pack_bf(w0, w1); zm7[i] = pack_bf(w2, w3);
    }
  uint32_t f3[3][4][4];
  {
    const uint32_t fa = tb + T_7 + 4 * (16 + x);
#pragma unroll
    for (int tt = 0; tt < 3; tt++)
#pragma unroll
      for (int D = 0; D < 4; D++) {
        const uint32_t a = fa + (tt == 0 ? 316 : (tt == 1 ? 320 : 0)) + 64 * D;
        f3[tt][D][0] = lds32(a); f3[tt][D][1] = lds32(a + 32); f3[tt][D][2] = lds32(a - 32); f3[tt][D][3] = lds32(a);
      }
  }
    SPLIT();
    nb_sync(NB_GATE, 256);
    SPLIT();
    float a[4][2][4];
#pragma unroll
    for (int kap = 0; kap < 4; kap++)
#pragma unroll
      for (int sg = 0; sg < 2; sg++)
#pragma unroll
        for (int bk = 3; bk >= kap; bk--) {
          const uint32_t(&q0_)[4] = f3[sg ? 2 : 0][bk - kap];
          const uint32_t(&q1_)[4] = f3[sg ? 2 : 1][bk - kap];
          float(&a0)[4] = a[bk][0];
          float(&a1)[4] = a[bk][1];
          if (sg == 0 && kap == 0) {
            mma0(a0[0], a0[1], a0[2], a0[3], q0_[0], q0_[1], q0_[2], q0_[3], z09[0], z09[1]);
            mma0(a1[0], a1[1], a1[2], a1[3], q1_[0], q1_[1], q1_[2], q1_[3], zm9[0], zm9[1]);
          } else {
            mma(a0[0], a0[1], a0[2], a0[3], q0_[0], q0_[1], q0_[2], q0_[3], sg ? zm7[2 * kap] : z09[2 * kap], sg ? zm7[2 * kap + 1] : z09[2 * kap + 1]);
            mma(a1[0], a1[1], a1[2], a1[3], q1_[0], q1_[1], q1_[2], q1_[3], sg ? z07[2 * kap] : zm9[2 * kap], sg ? z07[2 * kap + 1] : zm9[2 * kap + 1]);
          }
        }
    SPLIT();
#pragma unroll
    for (int i = 0; i < 8; i++) {
      uint32_t h[4];
      ldsm4(h, qa + 128 * i);
      const float ci[4] = {a[i >> 1][0][2 * (i & 1)], a[i >> 1][0][2 * (i & 1) + 1], a[i >> 1][1][2 * (i & 1)], a[i >> 1][1][2 * (i & 1) + 1]};
      mmac(acc[8 + i], h[0], h[1], h[2], h[3], lb0, lb1, ci);
    }
  }
  TS(44);
  {
    uint2 a5[10], a3[10];
    const uint32_t aa = tb + T_5 + 4 * (8 + 2 * g - 2 * c);
#pragma unroll
    for (int m = 0; m < 10; m++) { a5[m] = lds64(aa + 32 * m); a3[m] = lds64(aa + 384 + 32 * m); }
    uint32_t x5[12][2], x3[12][2];
    auto ygen = [&](int kap) {
#pragma unroll
      for (int hh = 0; hh < 2; hh++) {
        float y0, y1, y2, y3;
        mma0(y0, y1, y2, y3, by[0], by[1], by[2], by[3], lds32(y0a + 128 * kap + 64 * hh), lds32(y1a + 128 * kap + 64 * hh));
        x5[kap][hh] = pack_bf(y0, y1);
        x3[kap][hh] = pack_bf(y2, y3);
      }
    };
    ygen(11); ygen(10); ygen(9); ygen(8);
#pragma unroll
    for (int kap = 11; kap >= 0; kap--) {
      if (kap >= 4) ygen(kap - 4);
#pragma unroll
      for (int sg = 0; sg < 2; sg++)
#pragma unroll
        for (int i = 4; i >= 0; i--) {
          const int be = kap + 4 + i;
          if (be <= 15) {
            const uint2 &hi = sg ? a3[2 * i + 1] : a5[2 * i + 1], &lo = sg ? a3[2 * i] : a5[2 * i];
            const uint32_t b0 = sg ? x3[kap][0] : x5[kap][0], b1 = sg ? x3[kap][1] : x5[kap][1];
            if (be < 8 && i == 0 && sg == 0) mma0(acc[be][0], acc[be][1], acc[be][2], acc[be][3], hi.x, hi.y, lo.x, lo.y, b0, b1);
            else mma(acc[be][0], acc[be][1], acc[be][2], acc[be][3], hi.x, hi.y, lo.x, lo.y, b0, b1);
          }
        }
    }
  }
  TS(45);
  {
    const uint32_t st = tb + T_ST + lane * 8;
#pragma unroll
    for (int be = 4; be < 12; be++) sts64(st + 256 * be, pack_bf(acc[be][0], acc[be][1]), pack_bf(acc[be][2], acc[be][3]));
    SPLIT();
    uint32_t F[66], qd[8][4];
    const uint32_t fa = tb + T_D + 32 + 4 * x;
#pragma unroll
    for (int i = 0; i < 32; i++) {
      const int s = 120 - (i >> 2) - 8 * (i & 3);
      uint32_t(&q)[4] = qd[i & 7];
      ldsm4(q, qa + 16 * s);
      const int m = 16 * (i & 3) + 2 * (i >> 2);
      F[m] = lds32(fa + 32 * m); F[m + 1] = lds32(fa + 32 * m + 32);
#pragma unroll
      for (int be = 15; be >= 12; be--) {
        const int de = 8 * be - s;
        float(&a)[4] = (be >= 14 && !(i & 1)) ? acc[be - 4] : acc[be];
        if (de >= 0 && be >= 14 && i == 2 * (15 - be)) mma0(a[0], a[1], a[2], a[3], q[0], q[1], q[2], q[3], F[2 * de + 1], F[2 * de]);
        else if (de >= 0) mma(a[0], a[1], a[2], a[3], q[0], q[1], q[2], q[3], F[2 * de + 1], F[2 * de]);
      }
    }
#pragma unroll
    for (int i = 0; i < 8; i++) acc[14 + (i >> 2)][i & 3] += acc[10 + (i >> 2)][i & 3];
    F[64] = lds32(fa + 32 * 64); F[65] = lds32(fa + 32 * 65);
#pragma unroll
    for (int i = 0; i < 6; i++) ldsm4(qd[i], qa + 128 * 11 - 16 * i);
    uint2 sv = lds64(st + 256 * 11);
    float ci[4] = {bf_lo(sv.x), bf_hi(sv.x), bf_lo(sv.y), bf_hi(sv.y)};
    float T[5][4];
#pragma unroll
    for (int i = 0; i < 16; i++) T[i >> 2][i & 3] = acc[12 + (i >> 2)][i & 3];
    nb_sync(NB_YZ, 160);
    TS(46);
    uint32_t held[2];
#pragma unroll
    for (int be = 11; be >= 0; be--) {
      if (be & 1) SPLITN(be);
      const uint32_t qp = qa + 128 * be;
#pragma unroll
      for (int k = 4; k >= 1; k--) mmac(T[k], qd[0][0], qd[0][1], qd[0][2], qd[0][3], F[16 * k + 1], F[16 * k], T[k - 1]);
      if (be >= 4) mmac(T[0], qd[0][0], qd[0][1], qd[0][2], qd[0][3], F[1], F[0], ci);
      else mma0(T[0][0], T[0][1], T[0][2], T[0][3], qd[0][0], qd[0][1], qd[0][2], qd[0][3], F[1], F[0]);
      ldsm4(qd[6], qp - 16 * 6);
      ldsm4(qd[7], qp - 16 * 7);
      if (be > 4) sv = lds64(st + 256 * (be - 1));
#pragma unroll
      for (int i = 1; i < 8; i++) {
#pragma unroll
        for (int k = 3; k >= 0; k--)
          mma(T[k][0], T[k][1], T[k][2], T[k][3], qd[i][0], qd[i][1], qd[i][2], qd[i][3], F[16 * k + 2 * i + 1], F[16 * k + 2 * i]);
        if (i < 7 && be > 0) ldsm4(qd[i - 1], qp - 128 - 16 * (i - 1));
        if (i == 2) {
          const uint32_t w0 = pack_bf(T[4][0], T[4][1]), w1 = pack_bf(T[4][2], T[4][3]);
          if (be & 1) { held[0] = w0; held[1] = w1; }
          else st_x(ydst + (be + 4) * 16, nz(w0), w1, held[0], held[1]);
          if ((be & 3) == 3 && be < 11) nb_arrive(NB_Y + 2 + (be >> 2), 160);
        }
        if (i == 4 && be > 4) { ci[0] = bf_lo(sv.x); ci[1] = bf_hi(sv.x); ci[2] = bf_lo(sv.y); ci[3] = bf_hi(sv.y); }
      }
    }
    nb_arrive(NB_Y + 1, 160);
#pragma unroll
    for (int B = 1; B >= 0; B--)
      st_x(ydst + B * 32, nz(pack_bf(T[2 * B][0], T[2 * B][1])), pack_bf(T[2 * B][2], T[2 * B][3]),
           pack_bf(T[2 * B + 1][0], T[2 * B + 1][1]), pack_bf(T[2 * B + 1][2], T[2 * B + 1][3]));
  }
}

__device__ __forceinline__ void dual_exp(const uint32_t* w, uint32_t* e) {
  const float L = 1.44268798828125f;
  uint32_t mx = bmax2(bmax2(w[0], w[1]), bmax2(w[2], w[3]));
  uint32_t mn = bmin2(bmin2(w[0], w[1]), bmin2(w[2], w[3]));
  mx = bmax2(mx, __shfl_xor_sync(0xffffffffu, mx, 1));
  mn = bmin2(mn, __shfl_xor_sync(0xffffffffu, mn, 1));
  mx = bmax2(mx, __shfl_xor_sync(0xffffffffu, mx, 2));
  mn = bmin2(mn, __shfl_xor_sync(0xffffffffu, mn, 2));
  const float mx0 = bf_lo(mx) * -L, mx1 = bf_hi(mx) * -L, mn0 = bf_lo(mn) * L, mn1 = bf_hi(mn) * L;
#pragma unroll
  for (int i = 0; i < 2; i++) {
    const float a0 = bf_lo(w[2 * i]), a1 = bf_hi(w[2 * i]), b0 = bf_lo(w[2 * i + 1]), b1 = bf_hi(w[2 * i + 1]);
    e[2 * i] = pack_bf(ex2(fmaf(a0, L, mx0)), ex2(fmaf(b0, L, mx0)));
    e[2 * i + 1] = pack_bf(ex2(fmaf(a1, L, mx1)), ex2(fmaf(b1, L, mx1)));
    e[4 + 2 * i] = pack_bf(ex2(fmaf(a0, -L, mn0)), ex2(fmaf(b0, -L, mn0)));
    e[5 + 2 * i] = pack_bf(ex2(fmaf(a1, -L, mn1)), ex2(fmaf(b1, -L, mn1)));
  }
}
__device__ __forceinline__ void normalise(uint32_t* e, const float (&s)[4]) {
  const uint32_t r = pack_bf(rcp(s[0]), rcp(s[2]));
  const __nv_bfloat162 rr = *(const __nv_bfloat162*)&r;
#pragma unroll
  for (int i = 0; i < 4; i++) {
    const __nv_bfloat162 v = __hmul2(*(const __nv_bfloat162*)&e[i], (i & 1) ? __high2bfloat162(rr) : __low2bfloat162(rr));
    e[i] = *(const uint32_t*)&v;
  }
}
__host__ __device__ constexpr uint64_t qdesc(uint32_t addr) { return mkdesc(addr, 128, 256, 0); }

__global__ void __launch_bounds__(NTHREADS, 1)
fused_kernel(const Params P, const __grid_constant__ CUtensorMap mx, const __grid_constant__ CUtensorMap mw,
             const __grid_constant__ CUtensorMap mo, const __grid_constant__ CUtensorMap mu,
             const __grid_constant__ CUtensorMap mout) {
  constexpr uint32_t sb = SB;
  const int tid = threadIdx.x, lane = tid & 31;
  const int warp = __shfl_sync(0xffffffffu, tid >> 5, 0);
  const int b = blockIdx.x, oct = b >> 3, i8 = b & 7;
  const int rt = (((oct & 4) ? ~oct : oct) & 3) * 2 + (i8 >> 2);
  const int hp = (oct >> 2) * 4 + (i8 & 3);

  const int wg = warp >> 2, w = warp & 3;
  const int d = b * 4 + ((tid >> 5) & 3);
  const KgenRaw raw = kgen_load(P, d, (tid >> 7) & 1, lane, (tid + 128) & 256);
  const uint32_t tb = sb + OFF_T + w * T_CH;
  if (warp >= 12) {
    asm volatile("setmaxnreg.dec.sync.aligned.u32 32;");
    if (warp == 12) {
      if (lane == 0) {
#pragma unroll
        for (int i = 0; i < 9; i++) mbar_init(BAR(i), 1);
        asm volatile("fence.mbarrier_init.release.cluster;" ::: "memory");
      }
      __syncwarp();
      if (lane < 9) mbar_expect(BAR(0) + 8 * lane, lane == 0 ? 16384 : 28672);
      __syncwarp();
      nb_arrive(NB_PROD, 384);
#pragma unroll 1
      for (int kb = 0; kb < 8; kb++) {
        if (kb == U_AT) e_tma4d(sb + OFF_STG0, &mu, BAR(MB_URAW), i8 * 64, oct * 2);
        e_tma3d(sb + OFF_W + kb * 12288, &mw, BAR(MB_FULL) + 8 * kb, hp * 32, kb * 64, 0);
        if (kb < 5) e_tma2d(sb + OFF_X + (kb < 2 ? kb + 3 : kb - 2) * 16384, &mx, BAR(MB_FULL) + 8 * kb, kb * 64, rt * 256);
      }
      if (smem_u32(smem_raw) != SB) __trap();
      if (lane == 0) TS1(54);
      nb_sync(NB_GATE + 1, 64);
      e_prefetch(P.x + (size_t)(rt * 256 + 128 + hp * 8) * 512, 8192);
      uint32_t slot = sb + OFF_X + 3 * 16384;
#pragma unroll 1
      for (int n = 0; n < 11; n++) {
        mbar_spin(BAR(MB_EMPTY) + 8 * n);
        const int m = n + 5;
        e_tma2d(slot, &mx, BAR(MB_FULL) + 8 * m, (m & 7) * 64, rt * 256 + (m >> 3) * 128);
        slot = slot == sb + OFF_X + 4 * 16384 ? sb + OFF_X : slot + 16384;
        if (n == 7) {
          e_prefetch(P.wo + (size_t)b * 2048, 4096);
          asm volatile("prefetch.tensormap [%0];" ::"l"(&mo) : "memory");
          asm volatile("prefetch.tensormap [%0];" ::"l"(&mout) : "memory");
        }
      }
#pragma unroll 1
      for (int i = 0; i < 8; i++) {
        mbar_wait(BAR(MB_EMPTY + 10) + 8 * ((0x54332222u >> (4 * i)) & 7));
        const int w0 = (0x54736210u >> (4 * i)) & 7;
        e_tma3d(sb + OFF_W + w0 * 16384, &mo, BAR(MB_WO), 0, w0 * 64, (hp & 3) * 2);
      }
    } else {
      if (warp == 13) {
        if (lane == 0) {
#pragma unroll
          for (int i = 9; i < 39; i++) mbar_init(BAR(i), i < MB_EMPTY ? 1 : 4);
          asm volatile("fence.mbarrier_init.release.cluster;" ::: "memory");
        }
        __syncwarp();
        if (lane < 14 && lane != 9) mbar_expect(BAR(MB_FULL + 8) + 8 * lane, lane == 8 ? 131072 : (lane == 10 ? 8192 : (lane == 13 ? 24576 : 16384)));
        nb_arrive(NB_GATE + 1, 64);
      } else if (warp == 14) {
        asm volatile("prefetch.tensormap [%0];" ::"l"(&mw) : "memory");
        asm volatile("prefetch.tensormap [%0];" ::"l"(&mx) : "memory");
        asm volatile("prefetch.tensormap [%0];" ::"l"(&mu) : "memory");
        e_prefetch(P.x + (size_t)(rt * 256 + hp * 8) * 512, 8192);
      }
      nb_sync(NB_PROD, 384);
      if (warp == 15) {
        const uint4 v0 = __ldg((const uint4*)P.wphi + hp * 64 + lane), v1 = __ldg((const uint4*)P.wphi + hp * 64 + 32 + lane);
        sts128(sb + OFF_PHI + (lane & 1) * 256 + (lane >> 1) * 16, v0.x, v0.y, v0.z, v0.w);
        sts128(sb + OFF_PHI + 512 + (lane & 1) * 256 + (lane >> 1) * 16, v1.x, v1.y, v1.z, v1.w);
        const uint32_t one = (((lane >> 3) ^ (lane >> 4)) & 1) ? 0u : ((lane & 1) ? 0x3F800000u : 0x3F80u);
        const int q = (lane >> 1) & 3;
        sts128(sb + OFF_EYE + lane * 16, q == 0 ? one : 0u, q == 1 ? one : 0u, q == 2 ? one : 0u, q == 3 ? one : 0u);
        sts64(sb + OFF_ONE + lane * 8, 0x3F803F80u, 0x3F803F80u);
        asm volatile("fence.proxy.async.shared::cta;" ::: "memory");
        nb_arrive(NB_KREAD, 160);
      }
      uint32_t* cnt = (uint32_t*)(P.xs + X_CNT) + (warp == 13 ? i8 : (warp == 14 ? 8 + rt : 16 + oct)) * 32;
      const unsigned target = (ld_x32(cnt) & ~15u) + 16;
      if (warp != 14) {
        if (warp == 15) mbar_wait(BAR(MB_EMPTY + ZERO_STEP));
        uint4* pz = P.xs + (warp == 13 ? X_PART + (hp * 8 + rt) * 144 : X_Y + b * 1024) + lane;
#pragma unroll 1
        for (int i = (warp == 13 ? 144 : 1024) - lane; i > 0; i -= 32, pz += 32) st_x(pz, 0, 0, 0, 0);
      }
      if (warp == 15) __syncwarp();
      else nb_sync(warp == 13 ? NB_INIT : NB_ODONE, warp == 13 ? 160 : 288);
      if (lane == 0) asm volatile("red.release.gpu.global.add.u32 [%0], %1;" ::"l"(cnt), "r"(warp == 15 ? 2 : 1) : "memory");
      if (lane == 0) TS1(warp == 13 ? 50 : (warp == 14 ? 57 : 53));
      __syncwarp();
      if (warp == 14) nb_arrive(NB_GATE + 1, 160);
      asm volatile("fence.proxy.async.shared::cta;" ::: "memory");
      if (warp == 13) cnt += ((lane & 1 ? b >> 4 : i8 ^ (lane & 4)) - i8) * 32;
#pragma unroll 1
      for (int i = 0; i < SPIN_MAX; i++) {
        unsigned v;
        asm volatile("ld.acquire.gpu.global.u32 %0, [%1];" : "=r"(v) : "l"(cnt) : "memory");
        if (__all_sync(0xffffffffu, (int)(v - target) >= 0)) break;
      }
      if (lane == 0) TS1(warp == 13 ? 51 : (warp == 14 ? 58 : 55));
      if (warp == 15) { nb_arrive(NB_YZ, 160); return; }
      asm volatile("fence.proxy.async.global;" ::: "memory");
      if (warp == 13) {
        mbar_wait(BAR(MB_EMPTY + 11));
        e_expect(BAR(MB_UFULL), 4 * U_CH);
        e_bulk(sb + OFF_U, P.xs + X_UT + b * (U_CH / 4), 4 * U_CH, BAR(MB_UFULL));
      } else {
        const uint4* src = P.xs + X_O + (rt * 4 + (hp >> 2)) * 4096;
        e_bulk(sb + OFF_X + 32768 + 57344, src + 3584, 8192, BAR(MB_O));
        e_bulk(sb + OFF_X + 32768, src, 16384, BAR(MB_O + 1));
        e_bulk(sb + OFF_X + 49152, src + 1024, 16384, BAR(MB_O + 2));
        e_bulk(sb + OFF_STG0, src + 3200, 6144, BAR(MB_O + 3));
        nb_sync(NB_BDONE, 288);
        asm volatile("fence.proxy.async.shared::cta;" ::: "memory");
        e_bulk(sb + OFF_U, src + 2048, 18432, BAR(MB_O + 3));
      }
    }
    return;
  }

  asm volatile("setmaxnreg.inc.sync.aligned.u32 160;");
  const int t = tid & 127;
  const int g = lane >> 2, c = lane & 3;
  const uint32_t kp = ((tb + 127) & ~127u) + (wg & 1) * 2048;
  const KgenAddr kad = kgen_addr(lane, kp);
  if (wg) nb_sync(NB_PROD, 384);
  float k[5][4], k2048, ksc;
  if (wg) {
    kgen_unit(raw, kad, blockIdx.y, k, k2048, ksc);
    TS(40 + wg);
    if ((fu(k[0][0]) & fu(k[1][0]) & fu(k[2][0]) & fu(k[3][0]) & fu(k[4][0])) == 0xffffffffu) sts32(kp, 0);
  }
  if (wg) nb_arrive(0, 384);
  if (wg) {
    if (wg == 1) {
      uint32_t h[10];
#pragma unroll
      for (int j = 0; j < 10; j++) h[j] = hu(__floats2half2_rn(k[j >> 1][2 * (j & 1)], k[j >> 1][2 * (j & 1) + 1]));
      sts128(kp + lane * 16, h[0], h[1], h[2], h[3]);
      sts128(kp + 512 + lane * 16, h[4], h[5], h[6], h[7]);
      sts128(kp + 1024 + lane * 16, h[8], h[9], fu(k2048), fu(ksc));
      nb_arrive(NB_PREP, 256);
    }
  } else {
    nb_sync(NB_KREAD, 160);
    mbar_wait(BAR(MB_URAW));
    TS(48);
    uint4* dst = P.xs + X_UT + (i8 * 64 + g) * (U_CH / 16) + (w & 1) * (U_ODD / 16) + U_PAD / 16 + oct * 8 + (w >> 1) * 4 + c;
    const int ln = ((lane >> 1) & 3) + 4 * (lane & 1);
    uint32_t r[8][4];
#pragma unroll
    for (int i = 0; i < 8; i++) ldsm4t(r[i], sb + OFF_STG0 + w * 4096 + ((lane >> 3) * 8 + ln) * 128 + ((i ^ ln) << 4));
#pragma unroll
    for (int i = 0; i < 8; i++) dst[i * (U_CH / 2)] = make_uint4(r[i][0], r[i][1], r[i][2], r[i][3]);
    nb_arrive(NB_INIT, 160);
    nb_sync(0, 384);
  }
  {
    if (wg == 2) {
#pragma unroll
      for (int j = 0; j < 5; j++) { k[j][0] *= ksc; k[j][1] *= ksc; k[j][2] *= ksc; k[j][3] *= ksc; }
      const unsigned short dsk = __ldg((const unsigned short*)P.Dskip + d);
      nb_sync(NB_PREP, 256);
      {
        const uint32_t src = kp + 2048 + lane * 16;
        const uint4 v0 = lds128(src), v1 = lds128(src + 512), v2 = lds128(src + 1024);
        const uint32_t h[10] = {v0.x, v0.y, v0.z, v0.w, v1.x, v1.y, v1.z, v1.w, v2.x, v2.y};
#pragma unroll
        for (int j = 0; j < 10; j++) {
          const float2 f = __half22float2(*(const __half2*)&h[j]);
          k[j >> 1][2 * (j & 1)] = fmaf(f.x, uf(v2.w), k[j >> 1][2 * (j & 1)]);
          k[j >> 1][2 * (j & 1) + 1] = fmaf(f.y, uf(v2.w), k[j >> 1][2 * (j & 1) + 1]);
        }
        k2048 += uf(v2.z);
      }
#pragma unroll
      for (int o2 = 16; o2; o2 >>= 1) k2048 += __shfl_xor_sync(0xffffffffu, k2048, o2);
      if (lane == 0) k[0][0] += bf_lo(dsk);
      __syncwarp();
      TS(34);
      build_tables(tb, lane, k, k2048);
      TS(35);
      uint4* const g_y = P.xs + X_Y;
      conv_channel(sb + OFF_U + w * U_CH, tb, lane, g_y + (size_t)d * 256 + lane);
      nb_arrive(NB_BDONE, 288);
      nb_arrive(NB_Y, 160);
      TS(37);
      if (w == 0) TSDUMP(32);
      return;
    }
    if (wg == 1) {
      mbar_wait(BAR(MB_EMPTY + 4));
      mbar_spin(BAR(MB_EMPTY + 6));
    }
    TS(wg * 16 + 1);
  }

  float acc[2][48];
  {
    uint32_t fb = BAR(MB_FULL) + 64 * wg;
    uint32_t da = (uint32_t)mkdesc(sb + OFF_X, 16, 0, 0) + (wg ? 1024 : 3072), db = (uint32_t)mkdesc(sb + OFF_W, 4096, 0, 0);
    constexpr uint64_t ha = mkdesc(0, 0, 1024, 1), hb = mkdesc(0, 0, 512, 2);
    mbar_spin(fb);
    TS(wg * 16 + 2);
#pragma unroll 1
    for (int kb = 0; kb < 8; kb++) {
      WG_FENCE();
#pragma unroll
      for (int k = 0; k < 4; k++) {
        wgmma_ss_n96(acc[0], ha | (da + 2 * k), hb | (db + 64 * k), k ? 1 : kb);
        wgmma_ss_n96(acc[1], ha | (da + 2 * k + 512), hb | (db + 64 * k), k ? 1 : kb);
      }
      WG_COMMIT();
      if (kb < 7) mbar_spin(fb + 8);
      WG_WAIT(1);
      if (kb > 0) e_arrive(fb + 8 * (MB_EMPTY - MB_FULL - 1));
      fb += 8; db += 768;
      da = da == (uint32_t)mkdesc(sb + OFF_X + 65536, 16, 0, 0) ? da - 4096 : da + 1024;
    }
    WG_WAIT(0);
    e_arrive(fb + 8 * (MB_EMPTY - MB_FULL - 1));
    SPLIT();
  }
  TS(wg * 16 + 3);

  constexpr uint32_t stg0 = sb + OFF_STG0, stg1 = sb + OFF_X + 32768;
  uint4* const g_part = P.xs + X_PART;
  uint4* const g_o = P.xs + X_O;
  constexpr uint32_t kvs = stg0;
  auto pack8 = [](const float* a) { return make_uint4(pack_bf(a[0], a[1]), pack_bf(a[2], a[3]), pack_bf(a[4], a[5]), pack_bf(a[6], a[7])); };
  auto feat = [&](const uint4 (&af)[4], float (&p)[4][8]) {
    WG_FENCE();
#pragma unroll
    for (int u = 0; u < 4; u++) wgmma_rs_n16(p[u], af[u], qdesc(sb + OFF_PHI + (u & 1) * 512), 0);
    WG_COMMIT();
  };
  auto packp = [](const float (&p)[4][8], uint32_t (&pw)[16]) {
#pragma unroll
    for (int i = 0; i < 16; i++) pw[i] = pack_bf(p[i >> 2][(i & 1) + 2 * (i & 2)], p[i >> 2][(i & 1) + 2 * (i & 2) + 2]);
  };
  auto contract = [&](float (&kc)[20], uint32_t stg, int acc_in) {
    WG_FENCE();
#pragma unroll
    for (int s = 0; s < 8; s++) wgmma_ss_n40(kc, qdesc(stg + s * SLAB), qdesc(stg + s * SLAB + 2048), s ? 1 : acc_in);
    WG_COMMIT();
    WG_WAIT(0);
  };
  uint32_t eq[32];
  {
    uint4 af[4], aq[4], vp[4];
    float p[4][8];
#pragma unroll
    for (int u = 0; u < 4; u++) af[u] = pack8(acc[u >> 1] + 16 + 8 * (u & 1));
    feat(af, p);
#pragma unroll
    for (int u = 0; u < 4; u++) { aq[u] = pack8(acc[u >> 1] + 8 * (u & 1)); vp[u] = pack8(acc[u >> 1] + 32 + 8 * (u & 1)); }
    WG_WAIT(0);
    uint32_t pw[16], ek[32];
    packp(p, pw);
#pragma unroll
    for (int u = 0; u < 4; u++) dual_exp(pw + 4 * u, ek + 8 * u);
    TS(wg * 16 + 12);
    mbar_spin(BAR(MB_EMPTY + 7) + 64 * wg);
    float rs[8][4];
    WG_FENCE();
#pragma unroll
    for (int i = 0; i < 8; i++) wgmma_rs_n8(rs[i], make_uint4(ek[4 * i], ek[4 * i + 1], ek[4 * i + 2], ek[4 * i + 3]), qdesc(sb + OFF_ONE), 0);
    WG_COMMIT();
    feat(aq, p);
    const uint32_t sl = (wg ? stg1 : stg0) + w * SLAB + lane * 16;
#pragma unroll
    for (int i = 0; i < 4; i++) stsm4(sl + (i >> 1) * 4 * SLAB + 2048 + (i & 1) * 512, vp[i].x, vp[i].y, vp[i].z, vp[i].w);
    sts128(sl + (lane >> 4) * (4 * SLAB - 256) + 3072, 0x3F803F80u, 0x3F803F80u, 0x3F803F80u, 0x3F803F80u);
    WG_WAIT(1);
#pragma unroll
    for (int i = 0; i < 8; i++) {
      normalise(ek + 4 * i, rs[i]);
      stsm4(sl + (i >> 2) * 4 * SLAB + (i & 3) * 512, ek[4 * i], ek[4 * i + 1], ek[4 * i + 2], ek[4 * i + 3]);
    }
    asm volatile("fence.proxy.async.shared::cta;" ::: "memory");
    TS(wg * 16 + 13);
    if (wg) {
      nb_arrive(NB_ST0, 256);
      nb_arrive(NB_GATE, 256);
    } else {
      float kc[20];
      uint4* pp = g_part + (size_t)(hp * 8 + rt) * 144 + t;
      uint32_t* pz = (uint32_t*)(pp - t + 128) + w * 16 + c * 8 + g;
      asm volatile("" : "+l"(pp), "+l"(pz));
      nb_sync(NB_WG0, 128);
      contract(kc, stg0, 0);
      mbar_wait(BAR(MB_UFULL));
      TS(15);
      nb_sync(NB_ST0, 256);
      contract(kc, stg1, 1);
      TS(6);
      float kv[8];
#pragma unroll
      for (int i = 0; i < 8; i++) kv[i] = w & 2 ? kc[8 + i] : kc[i];
      st_x(pp, nz(pack_bf(kv[0], kv[1])), pack_bf(kv[2], kv[3]), pack_bf(kv[4], kv[5]), pack_bf(kv[6], kv[7]));
      if (c < 2) st_x32(pz, nz(fu(c ? kc[18] : kc[16])));
      TS(5);
    }
    SPLIT();
    WG_WAIT(0);
    packp(p, pw);
#pragma unroll
    for (int u = 0; u < 4; u++) dual_exp(pw + 4 * u, eq + 8 * u);
    SPLIT();
  }
  TS(wg * 16 + 4);
  if (wg == 1) {
    mbar_wait(BAR(MB_UFULL));
    const uint4* ps = g_part + (size_t)hp * 8 * 144 + t;
    const uint32_t* zs = (const uint32_t*)(g_part + (size_t)(hp * 8 + (lane >> 4) * 4) * 144 + 128) + w * 16 + (lane & 15);
    uint4 v[8];
    uint32_t zv[4];
#pragma unroll 1
    for (int it = 0; it < SPIN_MAX; it++) {
#pragma unroll
      for (int i = 0; i < 8; i++) v[i] = ld_x(ps + i * 144);
#pragma unroll
      for (int i = 0; i < 4; i++) zv[i] = ld_x32(zs + i * 576);
      uint32_t m = min(min(zv[0], zv[1]), min(zv[2], zv[3]));
#pragma unroll
      for (int i = 0; i < 8; i++) m = min(m, v[i].x);
      if (__all_sync(0xffffffffu, m != 0)) break;
    }
    float s[8];
    WG_FENCE();
#pragma unroll
    for (int r = 0; r < 8; r++) wgmma_rs_n16(s, v[r], qdesc(sb + OFF_EYE), r);
    WG_COMMIT();
    float zsum = (uf(zv[0]) + uf(zv[1])) + (uf(zv[2]) + uf(zv[3]));
    zsum += __shfl_xor_sync(0xffffffffu, zsum, 16);
    const uint32_t z1 = pack_bf(zsum, 1.f);
    if (lane < 16) sts128(kvs + w * 768 + 512 + lane * 16, z1, z1, z1, z1);
    WG_WAIT(0);
    stsm4(kvs + w * 768 + lane * 16, pack_bf(s[0], s[1]), pack_bf(s[2], s[3]), pack_bf(s[4], s[5]), pack_bf(s[6], s[7]));
    asm volatile("fence.proxy.async.shared::cta;" ::: "memory");
    TS(22);
  }
  nb_sync(NB_KV, 256);
  {
    float n[8][12];
    WG_FENCE();
#pragma unroll
    for (int i = 0; i < 8; i++) wgmma_rs_n24(n[i], make_uint4(eq[4 * i], eq[4 * i + 1], eq[4 * i + 2], eq[4 * i + 3]), qdesc(kvs + (i & 3) * 768), 0);
    WG_COMMIT();
    uint32_t* od = (uint32_t*)(g_o + (size_t)((rt * 4 + wg * 2) * 32 + hp * 2) * 128) + w * 64 + lane;
    WG_WAIT(0);
#pragma unroll
    for (int u = 0; u < 4; u++) {
      float(&np)[12] = n[2 * u];
      const float(&nm)[12] = n[2 * u + 1];
      const float q0 = np[9] * rcp(nm[9]), q1 = np[11] * rcp(nm[11]);
      const float r0 = rcp(fmaf(nm[8], q0, fmaf(np[9], 1e-6f, np[8]))), r1 = rcp(fmaf(nm[10], q1, fmaf(np[11], 1e-6f, np[10])));
#pragma unroll
      for (int i = 0; i < 8; i++) np[i] = fmaf(nm[i], (i & 2) ? q1 : q0, np[i]);
      uint32_t* o = od + (u >> 1) * 16384 + (u & 1) * 512;
      o[0] = pack_bf(np[0] * r0, np[1] * r0);
      o[32] = pack_bf(np[2] * r1, np[3] * r1);
      o[256] = pack_bf(np[4] * r0, np[5] * r0);
      o[288] = pack_bf(np[6] * r1, np[7] * r1);
      if (u == 1) SPLIT();
    }
  }
  TS(wg * 16 + 7);
  nb_arrive(NB_ODONE, 288);
  if (wg) {
    const uint4* src = P.xs + X_Y + (oct * 32 + c * 8) * 256 + (2 * w + (g >> 2)) * 32 + i8 * 4 + (g & 3);
    __nv_bfloat16* dst = P.out + (size_t)((2 * w + (g >> 2)) * 256 + i8 * 16 + (g & 3) * 2) * 1024 + 512 + oct * 32 + c * 8;
    nb_sync(NB_GATE + 1, 160);
    nb_sync(NB_Y + w, 160);
    uint4 v[8];
#pragma unroll 1
    for (int it = 0; it < SPIN_MAX; it++) {
      uint32_t m = 0xffffffffu;
#pragma unroll
      for (int i = 0; i < 8; i++) v[i] = ld_x(src + i * 256);
#pragma unroll
      for (int i = 0; i < 8; i++) m = min(m, v[i].x);
      if (__all_sync(0xffffffffu, m != 0)) break;
    }
#pragma unroll
    for (int i = 0; i < 8; i++) *(uint4*)(dst + (size_t)((i >> 2) * 128 + ((i >> 1) & 1) * 8 + (i & 1)) * 1024) = tr_row(v, i);
    TS(31);
    GT(63);
    if (w == 0) TSDUMP(16);
    return;
  }
  mbar_wait(BAR(MB_WO));
  nb_sync(NB_BDONE, 288);
  TS(8);
  mbar_spin(BAR(MB_O));
  TS(9);
  constexpr uint64_t ha = mkdesc(0, 0, 128, 0), hb = mkdesc(0, 0, 1024, 1);
  constexpr uint32_t da0 = (uint32_t)mkdesc(stg1, 1024, 0, 0), db0 = (uint32_t)mkdesc(sb + OFF_W, 8192, 0, 0);
  const uint32_t ot = ((sb + OFF_T + 1023) & ~1023u) + w * 4096;
  auto store_half = [&](const float* oc, int hf) {
#pragma unroll
    for (int i = 0; i < 8; i += 2)
      stsm4(ot + hf * 2048 + (lane & 15) * 128 + (((i + (lane >> 4)) ^ lane) & 7) * 16, pack_bf(oc[4 * i], oc[4 * i + 1]),
            pack_bf(oc[4 * i + 2], oc[4 * i + 3]), pack_bf(oc[4 * i + 4], oc[4 * i + 5]), pack_bf(oc[4 * i + 6], oc[4 * i + 7]));
    asm volatile("fence.proxy.async.shared::cta;" ::: "memory");
    __syncwarp();
    e_store2d(&mout, ot + hf * 2048, (hp & 3) * 128 + hf * 64, (rt * 4 + (hp >> 2)) * 64 + w * 16);
  };
  float oc[64];
#pragma unroll 1
  for (int j = 0; j < 8; j++) {
    const int kb = (j + 7) & 7;
    if ((j & 1) && j < 6) mbar_spin(BAR(MB_O + 1) + 4 * (j - 1));
    WG_FENCE();
#pragma unroll
    for (int k = 0; k < 4; k++) wgmma_ss_n128(oc, ha | (da0 + 512 * kb + 128 * k), hb | (db0 + 1024 * kb + 128 * k), k ? 1 : j);
    WG_COMMIT();
  }
  WG_WAIT(0);
  TS(10);
  store_half(oc, 0);
  store_half(oc + 32, 1);
  asm volatile(ELECT "cp.async.bulk.commit_group;\n@p cp.async.bulk.wait_group.read 0;\n}\n" ::: "memory");
  TS(wg * 16 + 11);
  GT(61 + wg);
  if (w == 0) TSDUMP(0);
  if (w == 1) TSDUMP(48);
}

typedef CUresult (*EncodeFn)(CUtensorMap*, CUtensorMapDataType, cuuint32_t, void*, const cuuint64_t*, const cuuint64_t*,
                             const cuuint32_t*, const cuuint32_t*, CUtensorMapInterleave, CUtensorMapSwizzle,
                             CUtensorMapL2promotion, CUtensorMapFloatOOBfill);

}

extern "C" void kernel_launch(void* const* d_in, const int* in_sizes, int n_in, void* d_out, int out_size) {
  (void)in_sizes; (void)n_in; (void)out_size;
  void* fn = nullptr;
  cudaDriverEntryPointQueryResult qr;
  cudaGetDriverEntryPoint("cuTensorMapEncodeTiled", &fn, cudaEnableDefault, &qr);
  EncodeFn enc = (EncodeFn)fn;
  CUtensorMap mx, mw, mo, mu, mout;
  const cuuint32_t es[5] = {1, 1, 1, 1, 1};
  {
    cuuint64_t dims[2] = {512, 2048}, st[1] = {1024};
    cuuint32_t box[2] = {64, 128};
    enc(&mx, CU_TENSOR_MAP_DATA_TYPE_BFLOAT16, 2, d_in[0], dims, st, box, es, CU_TENSOR_MAP_INTERLEAVE_NONE,
        CU_TENSOR_MAP_SWIZZLE_128B, CU_TENSOR_MAP_L2_PROMOTION_L2_128B, CU_TENSOR_MAP_FLOAT_OOB_FILL_NONE);
  }
  {
    cuuint64_t dims[3] = {512, 512, 3}, st[2] = {3072, 1024};
    cuuint32_t box[3] = {32, 64, 3};
    enc(&mw, CU_TENSOR_MAP_DATA_TYPE_BFLOAT16, 3, d_in[1], dims, st, box, es, CU_TENSOR_MAP_INTERLEAVE_NONE,
        CU_TENSOR_MAP_SWIZZLE_64B, CU_TENSOR_MAP_L2_PROMOTION_L2_128B, CU_TENSOR_MAP_FLOAT_OOB_FILL_NONE);
  }
  {
    cuuint64_t dims[3] = {64, 512, 8}, st[2] = {1024, 128};
    cuuint32_t box[3] = {64, 64, 2};
    enc(&mo, CU_TENSOR_MAP_DATA_TYPE_BFLOAT16, 3, d_in[3], dims, st, box, es, CU_TENSOR_MAP_INTERLEAVE_NONE,
        CU_TENSOR_MAP_SWIZZLE_128B, CU_TENSOR_MAP_L2_PROMOTION_L2_128B, CU_TENSOR_MAP_FLOAT_OOB_FILL_NONE);
  }
  {
    cuuint64_t dims[4] = {512, 4, 16, 32}, st[3] = {16384, 1024, 65536};
    cuuint32_t box[4] = {64, 4, 16, 2};
    enc(&mu, CU_TENSOR_MAP_DATA_TYPE_BFLOAT16, 4, d_in[4], dims, st, box, es, CU_TENSOR_MAP_INTERLEAVE_NONE,
        CU_TENSOR_MAP_SWIZZLE_128B, CU_TENSOR_MAP_L2_PROMOTION_L2_128B, CU_TENSOR_MAP_FLOAT_OOB_FILL_NONE);
  }
  {
    cuuint64_t dims[2] = {1024, 2048}, st[1] = {2048};
    cuuint32_t box[2] = {64, 16};
    enc(&mout, CU_TENSOR_MAP_DATA_TYPE_BFLOAT16, 2, d_out, dims, st, box, es, CU_TENSOR_MAP_INTERLEAVE_NONE,
        CU_TENSOR_MAP_SWIZZLE_128B, CU_TENSOR_MAP_L2_PROMOTION_NONE, CU_TENSOR_MAP_FLOAT_OOB_FILL_NONE);
  }
  Params P;
  P.x = (const __nv_bfloat16*)d_in[0];
  P.wphi = (const __nv_bfloat16*)d_in[2];
  P.wo = (const __nv_bfloat16*)d_in[3];
  P.logA = (const __nv_bfloat16*)d_in[5];
  P.Aim = (const __nv_bfloat16*)d_in[6];
  P.Cre = (const __nv_bfloat16*)d_in[7];
  P.Cim = (const __nv_bfloat16*)d_in[8];
  P.logdt = (const __nv_bfloat16*)d_in[9];
  P.Dskip = (const __nv_bfloat16*)d_in[10];
  P.out = (__nv_bfloat16*)d_out;
  cudaGetSymbolAddress((void**)&P.xs, g_x);
  P.ts = nullptr;
  cudaFuncSetAttribute(fused_kernel, cudaFuncAttributeMaxDynamicSharedMemorySize, SMEM_BYTES);
  fused_kernel<<<NCTA, NTHREADS, SMEM_BYTES>>>(P, mx, mw, mo, mu, mout);
}
```

```cpp
#include <cuda_runtime.h>
#include <cuda_bf16.h>
#include <cuda_fp16.h>
#include <cuda.h>
#include <stdint.h>

#define DBG_TS 0

namespace {

constexpr int NTHREADS = 512;
constexpr int NCTA = 128;
constexpr int OFF_W = 0;
constexpr int OFF_X = 98304;
constexpr int OFF_U = OFF_X + 65536;
constexpr int U_CH = 4416, U_ODD = 2240, U_PAD = 128;
constexpr int OFF_STG0 = OFF_U + 18432;
constexpr int SLAB = 3328;
constexpr int OFF_T = OFF_STG0 + 8 * SLAB;
constexpr int T_CH = 5216;
constexpr int T_D = 0;
constexpr int T_5 = 2144;
constexpr int T_3 = T_5 + 384;
constexpr int T_7 = T_5 + 1024;
constexpr int T_9 = T_7 + 320;
constexpr int T_KC = T_9 + 320;
constexpr int T_ST = T_5 - 1024;
constexpr int OFF_PHI = OFF_T + 4 * T_CH;
constexpr int OFF_EYE = OFF_PHI + 1024, OFF_ONE = OFF_EYE + 512;
constexpr int OFF_BAR = OFF_ONE + 256;
constexpr int SMEM_BYTES = OFF_BAR + 512 + 256 * DBG_TS;
constexpr uint32_t SB = 1024;
static_assert(T_KC + 2 * 656 <= T_CH, "table size");
static_assert(SMEM_BYTES <= 232448, "smem");
constexpr int MB_URAW = 0, MB_FULL = 1  , MB_WO = 17, MB_UFULL = 18, MB_O = 19  ,
              MB_EMPTY = 23  , MB_AUX = 39;
__host__ __device__ constexpr uint32_t BAR(int i) { return SB + OFF_BAR + 8 * i; }
constexpr int NB_WG0 = 1, NB_ODONE = 2, NB_ST0 = 3  , NB_KV = 5, NB_YZ = 6, NB_INIT = 7, NB_PREP = 8, NB_PROD = 9, NB_KREAD = 10, NB_BDONE = 11, NB_GATE = 12,
              NB_Y = 7  ;
#define GATE0 1
#define UAT 10
constexpr int U_AT = UAT;
constexpr int ZERO_STEP = 12;
constexpr int SPIN_MAX = 1 << 16;

constexpr int X_CNT = 0;
constexpr int X_PART = 256;
constexpr int X_O = X_PART + 16 * 8 * 144;
constexpr int X_Y = X_O + 32 * 32 * 128;
constexpr int X_UT = X_Y + 512 * 8 * 32;
constexpr int X_SIZE = X_UT + 512 * (U_CH / 16);
__device__ __align__(128) uint4 g_x[X_SIZE];
extern __shared__ uint8_t smem_raw[];
#define TS(i) do {} while (0)
#define TS1(i) do {} while (0)
#define GT(i) do {} while (0)
#define TSDUMP(base) do {} while (0)

__device__ __forceinline__ uint32_t smem_u32(const void* p) { return (uint32_t)__cvta_generic_to_shared(p); }
__device__ __forceinline__ void mbar_arrive(uint32_t b) {
  asm volatile("mbarrier.arrive.shared::cta.b64 _, [%0];" ::"r"(b) : "memory");
}
__device__ __forceinline__ void mbar_wait(uint32_t b) {
  uint32_t done = 0;
#pragma unroll 1
  for (int i = 0; i < SPIN_MAX && !done; i++) {
    asm volatile("{\n.reg .pred p;\nmbarrier.try_wait.parity.shared::cta.b64 p, [%1], 0, 4000;\nselp.u32 %0, 1, 0, p;\n}\n"
                 : "=r"(done) : "r"(b) : "memory");
  }
}
__device__ __forceinline__ void mbar_spin(uint32_t b) {
  uint32_t done = 0;
#pragma unroll 1
  for (int i = 0; i < (SPIN_MAX << 4) && !done; i++) {
    asm volatile("{\n.reg .pred p;\nmbarrier.try_wait.parity.shared::cta.b64 p, [%1], 0;\nselp.u32 %0, 1, 0, p;\n}\n"
                 : "=r"(done) : "r"(b) : "memory");
  }
}
__device__ __forceinline__ void mbar_init(uint32_t b, int n) {
  asm volatile("mbarrier.init.shared::cta.b64 [%0], %1;" ::"r"(b), "r"(n) : "memory");
}
__device__ __forceinline__ void mbar_expect(uint32_t b, int bytes) {
  asm volatile("mbarrier.arrive.expect_tx.shared::cta.b64 _, [%0], %1;" ::"r"(b), "r"(bytes) : "memory");
}
__device__ __forceinline__ void nb_sync(int id, int n) { asm volatile("bar.sync %0, %1;" ::"r"(id), "r"(n) : "memory"); }
__device__ __forceinline__ void nb_arrive(int id, int n) { asm volatile("bar.arrive %0, %1;" ::"r"(id), "r"(n) : "memory"); }
#define ELECT "{\n.reg .pred p;\nelect.sync _|p, 0xffffffff;\n@p "
__device__ __forceinline__ void e_arrive(uint32_t b) {
  asm volatile(ELECT "mbarrier.arrive.shared::cta.b64 _, [%0];\n}\n" ::"r"(b) : "memory");
}
__device__ __forceinline__ void e_expect(uint32_t b, int bytes) {
  asm volatile(ELECT "mbarrier.arrive.expect_tx.shared::cta.b64 _, [%0], %1;\n}\n" ::"r"(b), "r"(bytes) : "memory");
}
__device__ __forceinline__ void e_tma2d(uint32_t dst, const CUtensorMap* m, uint32_t bar, int c0, int c1) {
  asm volatile(ELECT "cp.async.bulk.tensor.2d.shared::cluster.global.mbarrier::complete_tx::bytes [%0], [%1, {%3,%4}], [%2];\n}\n"
               ::"r"(dst), "l"(m), "r"(bar), "r"(c0), "r"(c1) : "memory");
}
__device__ __forceinline__ void e_tma3d(uint32_t dst, const CUtensorMap* m, uint32_t bar, int c0, int c1, int c2) {
  asm volatile(ELECT "cp.async.bulk.tensor.3d.shared::cluster.global.mbarrier::complete_tx::bytes [%0], [%1, {%3,%4,%5}], [%2];\n}\n"
               ::"r"(dst), "l"(m), "r"(bar), "r"(c0), "r"(c1), "r"(c2) : "memory");
}
__device__ __forceinline__ void e_tma4d(uint32_t dst, const CUtensorMap* m, uint32_t bar, int c0, int c3) {
  asm volatile(ELECT "cp.async.bulk.tensor.4d.shared::cluster.global.mbarrier::complete_tx::bytes [%0], [%1, {%3,%5,%5,%4}], [%2];\n}\n"
               ::"r"(dst), "l"(m), "r"(bar), "r"(c0), "r"(c3), "r"(0) : "memory");
}
__device__ __forceinline__ void e_bulk(uint32_t dst, const void* src, int bytes, uint32_t bar) {
  asm volatile(ELECT "cp.async.bulk.shared::cluster.global.mbarrier::complete_tx::bytes [%0], [%1], %2, [%3];\n}\n"
               ::"r"(dst), "l"(src), "r"(bytes), "r"(bar) : "memory");
}
__device__ __forceinline__ void e_prefetch(const void* p, int bytes) {
  asm volatile(ELECT "cp.async.bulk.prefetch.L2.global [%0], %1;\n}\n" ::"l"(p), "r"(bytes) : "memory");
}
__device__ __forceinline__ void e_store2d(const CUtensorMap* m, uint32_t src, int c0, int c1) {
  asm volatile(ELECT "cp.async.bulk.tensor.2d.global.shared::cta.bulk_group [%0, {%2,%3}], [%1];\n}\n"
               ::"l"(m), "r"(src), "r"(c0), "r"(c1) : "memory");
}
__host__ __device__ constexpr uint64_t mkdesc(uint32_t addr, uint32_t lbo, uint32_t sbo, int swz) {
  return (uint64_t)((addr & 0x3FFFF) >> 4) | ((uint64_t)(lbo >> 4) << 16) | ((uint64_t)(sbo >> 4) << 32) |
         ((uint64_t)swz << 62);
}
#define SPLIT() asm volatile("{\n.reg .pred p;\nsetp.eq.u32 p, %0, %1;\n@p exit;\n}\n" ::"r"(blockIdx.y), "n"(__LINE__) : "memory")
#define SPLITN(n) asm volatile("{\n.reg .pred p;\nsetp.eq.u32 p, %0, %1;\n@p exit;\n}\n" ::"r"(blockIdx.y), "r"(4096 + (n)) : "memory")
#define WG_FENCE() asm volatile("wgmma.fence.sync.aligned;" ::: "memory")
#define WG_COMMIT() asm volatile("wgmma.commit_group.sync.aligned;" ::: "memory")
#define WG_WAIT(n) asm volatile("wgmma.wait_group.sync.aligned " #n ";" ::: "memory")

__device__ __forceinline__ void mma(float& d0, float& d1, float& d2, float& d3, uint32_t a0, uint32_t a1, uint32_t a2,
                                    uint32_t a3, uint32_t b0, uint32_t b1) {
  asm volatile("mma.sync.aligned.m16n8k16.row.col.f32.bf16.bf16.f32 {%0,%1,%2,%3},{%4,%5,%6,%7},{%8,%9},{%0,%1,%2,%3};"
               : "+f"(d0), "+f"(d1), "+f"(d2), "+f"(d3)
               : "r"(a0), "r"(a1), "r"(a2), "r"(a3), "r"(b0), "r"(b1));
}
__device__ __forceinline__ void mmac(float (&d)[4], uint32_t a0, uint32_t a1, uint32_t a2, uint32_t a3, uint32_t b0,
                                     uint32_t b1, const float (&c)[4]) {
  asm volatile("mma.sync.aligned.m16n8k16.row.col.f32.bf16.bf16.f32 {%0,%1,%2,%3},{%4,%5,%6,%7},{%8,%9},{%10,%11,%12,%13};"
               : "=f"(d[0]), "=f"(d[1]), "=f"(d[2]), "=f"(d[3])
               : "r"(a0), "r"(a1), "r"(a2), "r"(a3), "r"(b0), "r"(b1), "f"(c[0]), "f"(c[1]), "f"(c[2]), "f"(c[3]));
}
__device__ __forceinline__ void mma_p(int p, float (&d)[4], uint32_t a0, uint32_t a1, uint32_t a2, uint32_t a3, uint32_t b0, uint32_t b1) {
  asm volatile("{\n.reg .pred q;\nsetp.ne.b32 q, %10, 0;\n"
               "@q mma.sync.aligned.m16n8k16.row.col.f32.bf16.bf16.f32 {%0,%1,%2,%3},{%4,%5,%6,%7},{%8,%9},{%0,%1,%2,%3};\n}\n"
               : "+f"(d[0]), "+f"(d[1]), "+f"(d[2]), "+f"(d[3])
               : "r"(a0), "r"(a1), "r"(a2), "r"(a3), "r"(b0), "r"(b1), "r"(p));
}
__device__ __forceinline__ void mmac_p(int p, float (&d)[4], uint32_t a0, uint32_t a1, uint32_t a2, uint32_t a3, uint32_t b0,
                                       uint32_t b1, const float (&c)[4]) {
  asm volatile("{\n.reg .pred q;\nsetp.ne.b32 q, %14, 0;\n"
               "@q mma.sync.aligned.m16n8k16.row.col.f32.bf16.bf16.f32 {%0,%1,%2,%3},{%4,%5,%6,%7},{%8,%9},{%10,%11,%12,%13};\n}\n"
               : "+f"(d[0]), "+f"(d[1]), "+f"(d[2]), "+f"(d[3])
               : "r"(a0), "r"(a1), "r"(a2), "r"(a3), "r"(b0), "r"(b1), "f"(c[0]), "f"(c[1]), "f"(c[2]), "f"(c[3]), "r"(p));
}
__device__ __forceinline__ void mma_h(float (&d)[4], const uint32_t (&a)[4], uint32_t b0, uint32_t b1) {
  asm volatile("mma.sync.aligned.m16n8k16.row.col.f32.f16.f16.f32 {%0,%1,%2,%3},{%4,%5,%6,%7},{%8,%9},{%0,%1,%2,%3};"
               : "+f"(d[0]), "+f"(d[1]), "+f"(d[2]), "+f"(d[3]) : "r"(a[0]), "r"(a[1]), "r"(a[2]), "r"(a[3]), "r"(b0), "r"(b1));
}
__device__ __forceinline__ void mma0(float& d0, float& d1, float& d2, float& d3, uint32_t a0, uint32_t a1, uint32_t a2,
                                     uint32_t a3, uint32_t b0, uint32_t b1) {
  asm volatile("mma.sync.aligned.m16n8k16.row.col.f32.bf16.bf16.f32 {%0,%1,%2,%3},{%4,%5,%6,%7},{%8,%9},{%10,%10,%10,%10};"
               : "=f"(d0), "=f"(d1), "=f"(d2), "=f"(d3)
               : "r"(a0), "r"(a1), "r"(a2), "r"(a3), "r"(b0), "r"(b1), "f"(0.f));
}
__device__ __forceinline__ uint32_t pack_bf(float lo, float hi) {
  uint32_t r;
  asm("cvt.rn.bf16x2.f32 %0, %1, %2;" : "=r"(r) : "f"(hi), "f"(lo));
  return r;
}
__device__ __forceinline__ float bf_lo(uint32_t w) { return __uint_as_float(w << 16); }
__device__ __forceinline__ float bf_hi(uint32_t w) { return __uint_as_float(w & 0xffff0000u); }
__device__ __forceinline__ float bf_round(float x) { return __bfloat162float(__float2bfloat16_rn(x)); }
__device__ __forceinline__ uint32_t bmax2(uint32_t a, uint32_t b) {
  uint32_t r; asm("max.bf16x2 %0, %1, %2;" : "=r"(r) : "r"(a), "r"(b)); return r;
}
__device__ __forceinline__ uint32_t bmin2(uint32_t a, uint32_t b) {
  uint32_t r; asm("min.bf16x2 %0, %1, %2;" : "=r"(r) : "r"(a), "r"(b)); return r;
}
__device__ __forceinline__ float ex2(float x) { float r; asm("ex2.approx.ftz.f32 %0, %1;" : "=f"(r) : "f"(x)); return r; }
__device__ __forceinline__ float rcp(float x) { float r; asm("rcp.approx.ftz.f32 %0, %1;" : "=f"(r) : "f"(x)); return r; }
__device__ __forceinline__ void ldsm4(uint32_t (&r)[4], uint32_t a) {
  asm volatile("ldmatrix.sync.aligned.m8n8.x4.shared.b16 {%0,%1,%2,%3}, [%4];"
               : "=r"(r[0]), "=r"(r[1]), "=r"(r[2]), "=r"(r[3]) : "r"(a) : "memory");
}
__device__ __forceinline__ void ldsm4t(uint32_t (&r)[4], uint32_t a) {
  asm volatile("ldmatrix.sync.aligned.m8n8.x4.trans.shared.b16 {%0,%1,%2,%3}, [%4];"
               : "=r"(r[0]), "=r"(r[1]), "=r"(r[2]), "=r"(r[3]) : "r"(a) : "memory");
}
__device__ __forceinline__ void stsm4(uint32_t a, uint32_t r0, uint32_t r1, uint32_t r2, uint32_t r3) {
  asm volatile("stmatrix.sync.aligned.m8n8.x4.shared.b16 [%0], {%1,%2,%3,%4};"
               ::"r"(a), "r"(r0), "r"(r1), "r"(r2), "r"(r3) : "memory");
}
__device__ __forceinline__ uint32_t lds32(uint32_t a) {
  uint32_t r; asm volatile("ld.shared.u32 %0, [%1];" : "=r"(r) : "r"(a) : "memory"); return r;
}
__device__ __forceinline__ uint32_t lds16(uint32_t a) {
  uint32_t r; asm volatile("{\n.reg .u16 h;\nld.shared.u16 h, [%1];\ncvt.u32.u16 %0, h;\n}\n" : "=r"(r) : "r"(a) : "memory"); return r;
}
__device__ __forceinline__ uint2 lds64(uint32_t a) {
  uint2 r; asm volatile("ld.shared.v2.u32 {%0,%1}, [%2];" : "=r"(r.x), "=r"(r.y) : "r"(a) : "memory"); return r;
}
__device__ __forceinline__ uint4 lds128(uint32_t a) {
  uint4 r;
  asm volatile("ld.shared.v4.u32 {%0,%1,%2,%3}, [%4];" : "=r"(r.x), "=r"(r.y), "=r"(r.z), "=r"(r.w) : "r"(a) : "memory");
  return r;
}
__device__ __forceinline__ void sts32(uint32_t a, uint32_t v) { asm volatile("st.shared.u32 [%0], %1;" ::"r"(a), "r"(v) : "memory"); }
__device__ __forceinline__ void sts16(uint32_t a, uint32_t v) {
  asm volatile("{\n.reg .u16 h;\ncvt.u16.u32 h, %1;\nst.shared.u16 [%0], h;\n}\n" ::"r"(a), "r"(v) : "memory");
}
__device__ __forceinline__ void sts64(uint32_t a, uint32_t x, uint32_t y) {
  asm volatile("st.shared.v2.u32 [%0], {%1,%2};" ::"r"(a), "r"(x), "r"(y) : "memory");
}
__device__ __forceinline__ void sts128(uint32_t a, uint32_t x, uint32_t y, uint32_t z, uint32_t w) {
  asm volatile("st.shared.v4.u32 [%0], {%1,%2,%3,%4};" ::"r"(a), "r"(x), "r"(y), "r"(z), "r"(w) : "memory");
}
__device__ __forceinline__ uint4 ld_x(const uint4* p) {
  uint4 r;
  asm volatile("{\n.reg .b128 t;\nld.relaxed.gpu.global.b128 t, [%4];\nmov.b128 {%0,%1,%2,%3}, t;\n}\n"
               : "=r"(r.x), "=r"(r.y), "=r"(r.z), "=r"(r.w) : "l"(p) : "memory");
  return r;
}
__device__ __forceinline__ uint32_t ld_x32(const uint32_t* p) {
  uint32_t r; asm volatile("ld.relaxed.gpu.global.u32 %0, [%1];" : "=r"(r) : "l"(p) : "memory"); return r;
}
__device__ __forceinline__ void st_x(uint4* p, uint32_t x, uint32_t y, uint32_t z, uint32_t w) {
  asm volatile("{\n.reg .b128 t;\nmov.b128 t, {%1,%2,%3,%4};\nst.relaxed.gpu.global.b128 [%0], t;\n}\n"
               ::"l"(p), "r"(x), "r"(y), "r"(z), "r"(w) : "memory");
}
__device__ __forceinline__ void st_x_p(int p, uint4* a, uint32_t x, uint32_t y, uint32_t z, uint32_t w) {
  asm volatile("{\n.reg .b128 t;\n.reg .pred q;\nsetp.ne.b32 q, %5, 0;\nmov.b128 t, {%1,%2,%3,%4};\n@q st.relaxed.gpu.global.b128 [%0], t;\n}\n"
               ::"l"(a), "r"(x), "r"(y), "r"(z), "r"(w), "r"(p) : "memory");
}
__device__ __forceinline__ void sts64_p(int p, uint32_t a, uint32_t x, uint32_t y) {
  asm volatile("{\n.reg .pred q;\nsetp.ne.b32 q, %3, 0;\n@q st.shared.v2.u32 [%0], {%1,%2};\n}\n" ::"r"(a), "r"(x), "r"(y), "r"(p) : "memory");
}
__device__ __forceinline__ void st_x32(uint32_t* p, uint32_t x) {
  asm volatile("st.relaxed.gpu.global.u32 [%0], %1;" ::"l"(p), "r"(x) : "memory");
}
__device__ __forceinline__ uint32_t nz(uint32_t w) { return max(w, 1u); }
__device__ __forceinline__ uint32_t fu(float x) { return __float_as_uint(x); }
__device__ __forceinline__ float uf(uint32_t x) { return __uint_as_float(x); }

__device__ __forceinline__ void wgmma_ss_n96(float (&d)[48], uint64_t da, uint64_t db, int sc) {
  asm volatile("{\n.reg .pred p;\nsetp.ne.b32 p, %50, 0;\n"
      "wgmma.mma_async.sync.aligned.m64n96k16.f32.bf16.bf16 "
      "{%0,%1,%2,%3,%4,%5,%6,%7,%8,%9,%10,%11,%12,%13,%14,%15,%16,%17,%18,%19,%20,%21,%22,%23,%24,%25,%26,%27,%28,%29,%30,%31,%32,%33,%34,%35,%36,%37,%38,%39,%40,%41,%42,%43,%44,%45,%46,%47}, "
      "%48, %49, p, 1, 1, 0, 1;\n}\n"
      : "+f"(d[0]), "+f"(d[1]), "+f"(d[2]), "+f"(d[3]), "+f"(d[4]), "+f"(d[5]), "+f"(d[6]), "+f"(d[7]),
        "+f"(d[8]), "+f"(d[9]), "+f"(d[10]), "+f"(d[11]), "+f"(d[12]), "+f"(d[13]), "+f"(d[14]), "+f"(d[15]),
        "+f"(d[16]), "+f"(d[17]), "+f"(d[18]), "+f"(d[19]), "+f"(d[20]), "+f"(d[21]), "+f"(d[22]), "+f"(d[23]),
        "+f"(d[24]), "+f"(d[25]), "+f"(d[26]), "+f"(d[27]), "+f"(d[28]), "+f"(d[29]), "+f"(d[30]), "+f"(d[31]),
        "+f"(d[32]), "+f"(d[33]), "+f"(d[34]), "+f"(d[35]), "+f"(d[36]), "+f"(d[37]), "+f"(d[38]), "+f"(d[39]),
        "+f"(d[40]), "+f"(d[41]), "+f"(d[42]), "+f"(d[43]), "+f"(d[44]), "+f"(d[45]), "+f"(d[46]), "+f"(d[47])
      : "l"(da), "l"(db), "r"(sc));
}

__device__ __forceinline__ void wgmma_ss_n128(float (&d)[64], uint64_t da, uint64_t db, int sc) {
  asm volatile("{\n.reg .pred p;\nsetp.ne.b32 p, %66, 0;\n"
      "wgmma.mma_async.sync.aligned.m64n128k16.f32.bf16.bf16 "
      "{%0,%1,%2,%3,%4,%5,%6,%7,%8,%9,%10,%11,%12,%13,%14,%15,%16,%17,%18,%19,%20,%21,%22,%23,%24,%25,%26,%27,%28,%29,%30,%31,%32,%33,%34,%35,%36,%37,%38,%39,%40,%41,%42,%43,%44,%45,%46,%47,%48,%49,%50,%51,%52,%53,%54,%55,%56,%57,%58,%59,%60,%61,%62,%63}, "
      "%64, %65, p, 1, 1, 0, 1;\n}\n"
      : "+f"(d[0]), "+f"(d[1]), "+f"(d[2]), "+f"(d[3]), "+f"(d[4]), "+f"(d[5]), "+f"(d[6]), "+f"(d[7]),
        "+f"(d[8]), "+f"(d[9]), "+f"(d[10]), "+f"(d[11]), "+f"(d[12]), "+f"(d[13]), "+f"(d[14]), "+f"(d[15]),
        "+f"(d[16]), "+f"(d[17]), "+f"(d[18]), "+f"(d[19]), "+f"(d[20]), "+f"(d[21]), "+f"(d[22]), "+f"(d[23]),
        "+f"(d[24]), "+f"(d[25]), "+f"(d[26]), "+f"(d[27]), "+f"(d[28]), "+f"(d[29]), "+f"(d[30]), "+f"(d[31]),
        "+f"(d[32]), "+f"(d[33]), "+f"(d[34]), "+f"(d[35]), "+f"(d[36]), "+f"(d[37]), "+f"(d[38]), "+f"(d[39]),
        "+f"(d[40]), "+f"(d[41]), "+f"(d[42]), "+f"(d[43]), "+f"(d[44]), "+f"(d[45]), "+f"(d[46]), "+f"(d[47]),
        "+f"(d[48]), "+f"(d[49]), "+f"(d[50]), "+f"(d[51]), "+f"(d[52]), "+f"(d[53]), "+f"(d[54]), "+f"(d[55]),
        "+f"(d[56]), "+f"(d[57]), "+f"(d[58]), "+f"(d[59]), "+f"(d[60]), "+f"(d[61]), "+f"(d[62]), "+f"(d[63])
      : "l"(da), "l"(db), "r"(sc));
}

__device__ __forceinline__ void wgmma_ss_n40(float (&d)[20], uint64_t da, uint64_t db, int sc) {
  asm volatile("{\n.reg .pred p;\nsetp.ne.b32 p, %22, 0;\n"
      "wgmma.mma_async.sync.aligned.m64n40k16.f32.bf16.bf16 "
      "{%0,%1,%2,%3,%4,%5,%6,%7,%8,%9,%10,%11,%12,%13,%14,%15,%16,%17,%18,%19}, "
      "%20, %21, p, 1, 1, 1, 1;\n}\n"
      : "+f"(d[0]), "+f"(d[1]), "+f"(d[2]), "+f"(d[3]), "+f"(d[4]), "+f"(d[5]), "+f"(d[6]), "+f"(d[7]),
        "+f"(d[8]), "+f"(d[9]), "+f"(d[10]), "+f"(d[11]), "+f"(d[12]), "+f"(d[13]), "+f"(d[14]), "+f"(d[15]),
        "+f"(d[16]), "+f"(d[17]), "+f"(d[18]), "+f"(d[19])
      : "l"(da), "l"(db), "r"(sc));
}

__device__ __forceinline__ void wgmma_rs_n8(float (&d)[4], const uint4& a, uint64_t db, int sc) {
  asm volatile("{\n.reg .pred p;\nsetp.ne.b32 p, %9, 0;\n"
      "wgmma.mma_async.sync.aligned.m64n8k16.f32.bf16.bf16 "
      "{%0,%1,%2,%3}, "
      "{%4,%5,%6,%7}, %8, p, 1, 1, 1;\n}\n"
      : "+f"(d[0]), "+f"(d[1]), "+f"(d[2]), "+f"(d[3])
      : "r"(a.x), "r"(a.y), "r"(a.z), "r"(a.w), "l"(db), "r"(sc));
}

__device__ __forceinline__ void wgmma_rs_n16(float (&d)[8], const uint4& a, uint64_t db, int sc) {
  asm volatile("{\n.reg .pred p;\nsetp.ne.b32 p, %13, 0;\n"
      "wgmma.mma_async.sync.aligned.m64n16k16.f32.bf16.bf16 "
      "{%0,%1,%2,%3,%4,%5,%6,%7}, "
      "{%8,%9,%10,%11}, %12, p, 1, 1, 1;\n}\n"
      : "+f"(d[0]), "+f"(d[1]), "+f"(d[2]), "+f"(d[3]), "+f"(d[4]), "+f"(d[5]), "+f"(d[6]), "+f"(d[7])
      : "r"(a.x), "r"(a.y), "r"(a.z), "r"(a.w), "l"(db), "r"(sc));
}

__device__ __forceinline__ void wgmma_rs_n24(float (&d)[12], const uint4& a, uint64_t db, int sc) {
  asm volatile("{\n.reg .pred p;\nsetp.ne.b32 p, %17, 0;\n"
      "wgmma.mma_async.sync.aligned.m64n24k16.f32.bf16.bf16 "
      "{%0,%1,%2,%3,%4,%5,%6,%7,%8,%9,%10,%11}, "
      "{%12,%13,%14,%15}, %16, p, 1, 1, 1;\n}\n"
      : "+f"(d[0]), "+f"(d[1]), "+f"(d[2]), "+f"(d[3]), "+f"(d[4]), "+f"(d[5]), "+f"(d[6]), "+f"(d[7]),
        "+f"(d[8]), "+f"(d[9]), "+f"(d[10]), "+f"(d[11])
      : "r"(a.x), "r"(a.y), "r"(a.z), "r"(a.w), "l"(db), "r"(sc));
}

struct Params {
  const __nv_bfloat16 *logA, *Aim, *Cre, *Cim, *logdt, *Dskip, *x, *u, *wphi, *wo;
  __nv_bfloat16* out;
  uint4* xs;
  long long* ts;
};

__device__ __forceinline__ uint4 tr_row(const uint4 (&v)[8], int i) {
  uint32_t o[4];
#pragma unroll
  for (int m = 0; m < 4; m++) {
    const uint4 &ra = v[2 * m], &rb = v[2 * m + 1];
    const int k = i >> 1;
    const uint32_t xa = k == 0 ? ra.x : k == 1 ? ra.y : k == 2 ? ra.z : ra.w;
    const uint32_t xb = k == 0 ? rb.x : k == 1 ? rb.y : k == 2 ? rb.z : rb.w;
    o[m] = __byte_perm(xa, xb, (i & 1) ? 0x7632 : 0x5410);
  }
  return make_uint4(o[0], o[1], o[2], o[3]);
}

struct cpx { float r, i; };
__device__ __forceinline__ cpx csq(cpx a) { return {a.r * a.r - a.i * a.i, 2.f * (a.r * a.i)}; }
__device__ __forceinline__ cpx polar(float e, float t) {
  const float m = ex2(e);
  return {m * __cosf(t), m * __sinf(t)};
}

struct KgenRaw { uint32_t la, ai, cr, ci, ldt; };
__device__ __forceinline__ KgenRaw kgen_load(const Params& P, int d, int unit, int lane, int on) {
  const int o = d * 64 + unit * 32 + lane;
  KgenRaw r = {0, 0, 0, 0, 0};
  asm volatile("{\n.reg .pred p;\nsetp.ne.b32 p, %10, 0;\n@p ld.global.nc.u32 %0, [%5];\n@p ld.global.nc.u32 %1, [%6];\n"
               "@p ld.global.nc.u32 %2, [%7];\n@p ld.global.nc.u32 %3, [%8];\n@p ld.global.nc.u16 %4, [%9];\n}\n"
               : "+r"(r.la), "+r"(r.ai), "+r"(r.cr), "+r"(r.ci), "+r"(r.ldt)
               : "l"((const uint32_t*)P.logA + o), "l"((const uint32_t*)P.Aim + o), "l"((const uint32_t*)P.Cre + o),
                 "l"((const uint32_t*)P.Cim + o), "l"(P.logdt + d), "r"(on));
  return r;
}
struct hc { __half2 r, i; };
struct cpx2 { cpx a, b; };
__device__ __forceinline__ cpx2 csq2(const cpx2& v) { return {csq(v.a), csq(v.b)}; }
__device__ __forceinline__ hc toh(const cpx2& v) { return {__floats2half2_rn(v.a.r, v.b.r), __floats2half2_rn(v.a.i, v.b.i)}; }
__device__ __forceinline__ hc hmul(const hc& z, const hc& w) {
  return {__hfma2(z.r, w.r, __hneg2(__hmul2(z.i, w.i))), __hfma2(z.r, w.i, __hmul2(z.i, w.r))};
}
__device__ __forceinline__ hc hmulc(const hc& z, const hc& w) {
  return {__hfma2(z.r, w.r, __hmul2(z.i, w.i)), __hfma2(z.i, w.r, __hneg2(__hmul2(z.r, w.i)))};
}
__device__ __forceinline__ uint32_t hu(__half2 v) { return *(const uint32_t*)&v; }
__device__ __forceinline__ __half2 uh(uint32_t v) { return *(const __half2*)&v; }

struct KgenAddr { uint32_t sa, lb, lm[4]; };
__device__ __forceinline__ KgenAddr kgen_addr(int lane, uint32_t buf) {
  KgenAddr a;
  a.sa = buf + (lane & 7) * 128 + ((((lane >> 3) ^ lane) & 7) << 4);
  const int q = lane >> 4;
  const uint32_t b = buf + ((lane >> 3) & 1) * 1024 + q * 128;
  a.lb = b + (((lane ^ q) & 7) << 4);
  a.lm[0] = b + (q << 4);
  a.lm[1] = b + ((1 ^ q) << 4);
  a.lm[2] = b + (((2 + (lane & 1)) ^ q) << 4);
  a.lm[3] = b + (((4 + (lane & 3)) ^ q) << 4);
  asm volatile("" : "+r"(a.sa), "+r"(a.lb), "+r"(a.lm[0]), "+r"(a.lm[1]), "+r"(a.lm[2]), "+r"(a.lm[3]));
  return a;
}
struct KgenOps { uint32_t A[8][4], B[5][4][4]; };
__device__ __forceinline__ void kgen_unit(const KgenRaw& r, const KgenAddr& ad, uint32_t zero, KgenOps& op, float& k2048, float& sc) {
  const float dt = bf_round(expf(bf_lo(r.ldt)));
  const uint32_t ar = pack_bf(ex2(bf_lo(r.la) * 1.4426950408889634f), ex2(bf_hi(r.la) * 1.4426950408889634f));
  const float ca = dt * -1.4426950408889634f, a0 = bf_lo(ar) * ca, a1 = bf_hi(ar) * ca;
  const float f0 = bf_lo(r.ai) * dt, f1 = bf_hi(r.ai) * dt;
  const float r0 = f0 * 20.21267777267071f, r1 = f1 * 20.21267777267071f;
  const uint32_t cm = __vmaxu2(r.cr & 0x7fff7fffu, r.ci & 0x7fff7fffu);
  const uint32_t ex = min(max(__reduce_max_sync(0xffffffffu, max(cm >> 16, cm & 0xffffu)) >> 7, 1u), 253u);
  const float cs = uf((254u - ex) << 23);
  sc = 2.f * dt * uf(ex << 23);
  const cpx2 C = {{bf_lo(r.cr) * cs, bf_lo(r.ci) * -cs}, {bf_hi(r.cr) * cs, bf_hi(r.ci) * -cs}};
  auto put = [&](const hc (&v)[8]) {
    stsm4(ad.sa, hu(v[0].r), hu(v[1].r), hu(v[2].r), hu(v[3].r));
    stsm4(ad.sa + 1024, hu(v[0].i), hu(v[1].i), hu(v[2].i), hu(v[3].i));
    stsm4(ad.sa ^ 64, hu(v[4].r), hu(v[5].r), hu(v[6].r), hu(v[7].r));
    stsm4((ad.sa ^ 64) + 1024, hu(v[4].i), hu(v[5].i), hu(v[6].i), hu(v[7].i));
    __syncwarp();
  };
  auto get = [&](uint32_t (&o)[4][4], uint32_t a) {
#pragma unroll
    for (int i = 0; i < 4; i++) ldsm4(o[i], (a ^ (i << 5)) + i * 256);
  };
  auto at = [](const uint32_t (&o)[4][4], int s) { return hc{uh(o[s >> 1][2 * (s & 1)]), uh(o[s >> 1][2 * (s & 1) + 1])}; };
  uint32_t(&A)[8][4] = op.A;
  const cpx2 w1 = {polar(a0, f0), polar(a1, f1)};
  const cpx2 w127 = {polar(a0 * 127.f, (r0 - rintf(r0)) * 6.283185307179586f), polar(a1 * 127.f, (r1 - rintf(r1)) * 6.283185307179586f)};
  const cpx2 w2 = csq2(w1), w4 = csq2(w2);
  uint32_t(&T0)[4][4] = op.B[0];
  uint32_t(&X)[4][4] = op.B[4];
  uint32_t(*M)[4][4] = op.B + 1;
  {
    hc t[8];
    t[0] = {uh(0x3C003C00u), uh(0u)}; t[1] = toh(w1); t[2] = toh(w2); t[4] = toh(w4);
    t[3] = hmul(t[1], t[2]); t[5] = hmul(t[1], t[4]); t[6] = hmul(t[2], t[4]); t[7] = hmul(t[3], t[4]);
    put(t); get(T0, ad.lb);
  }
  const cpx2 w8 = csq2(w4), w16 = csq2(w8), w32 = csq2(w16), w64 = csq2(w32);
  {
    const hc m8 = toh(w8), m16 = toh(w16), m32 = toh(w32);
    hc a[8];
    a[0] = toh(C); a[1] = hmulc(a[0], m8);
    a[2] = hmulc(a[0], m16); a[3] = hmulc(a[1], m16);
#pragma unroll
    for (int i = 0; i < 4; i++) a[4 + i] = hmulc(a[i], m32);
    put(a); get(X, ad.lb);
  }
    const cpx2 w128 = {{w127.a.r * w1.a.r - w127.a.i * w1.a.i, w127.a.r * w1.a.i + w127.a.i * w1.a.r},
                     {w127.b.r * w1.b.r - w127.b.i * w1.b.i, w127.b.r * w1.b.i + w127.b.i * w1.b.r}};
  const cpx2 w256 = csq2(w128), w512 = csq2(w256);
  const hc m128 = toh(w128), m256 = toh(w256), m512 = toh(w512);
  {
    const hc m254 = toh(csq2(w127)), m127 = toh(w127);
    hc m[8];
    m[0] = toh(w64); m[1] = m128; m[2] = m256; m[3] = hmul(m127, m256);
    m[4] = m512; m[5] = hmul(m127, m512); m[6] = hmul(m[4], m254); m[7] = hmul(m[5], m254);
    put(m);
    get(M[0], ad.lm[0]);
#pragma unroll
    for (int s = 0; s < 8; s++) {
      const hc z = at(X, s), y = hmulc(z, at(M[0], s));
      A[s][0] = hu(z.r) + zero; A[s][1] = hu(y.r); A[s][2] = hu(z.i) + zero; A[s][3] = hu(y.i);
    }
#pragma unroll
    for (int i = 0; i < 3; i++) get(M[i], ad.lm[i + 1]);
  }
  const cpx2 w1024 = csq2(w512), we = csq2(w1024);
  {
    hc t[8];
    t[0] = toh(w1024); t[1] = hmul(t[0], m128);
    t[2] = hmul(t[0], m256); t[3] = hmul(t[1], m256);
#pragma unroll
    for (int i = 0; i < 4; i++) t[4 + i] = hmul(t[i], m512);
    put(t); get(X, ad.lb);
  }
  k2048 = (C.a.r * we.a.r + C.a.i * we.a.i + C.b.r * we.b.r + C.b.i * we.b.i) * sc;
#pragma unroll
  for (int j = 0; j < 3; j++)
#pragma unroll
    for (int s = 0; s < 8; s++) {
      const hc y = hmul(at(T0, s), at(M[j], s));
      M[j][s >> 1][2 * (s & 1)] = hu(y.r); M[j][s >> 1][2 * (s & 1) + 1] = hu(y.i);
    }
}
__device__ __forceinline__ void kgen_burst(const KgenOps& op, float (&k)[5][4]) {
#pragma unroll
  for (int j = 0; j < 5; j++) k[j][0] = k[j][1] = k[j][2] = k[j][3] = 0.f;
#pragma unroll
  for (int s = 0; s < 8; s++)
#pragma unroll
    for (int j = 0; j < 5; j++) mma_h(k[j], op.A[s], op.B[j][s >> 1][2 * (s & 1)], op.B[j][s >> 1][2 * (s & 1) + 1]);
}

__device__ __forceinline__ void build_tables(uint32_t tb, int lane, float (&k)[5][4], float k2048) {
  const int g = lane >> 2, c = lane & 3;
  const uint32_t kc = tb + T_KC + 16;
  {
    const uint32_t a0 = kc + 16 * g + 4 * c, a2 = kc + 2 * (256 + 4 * g + c);
    const uint32_t a3 = kc + 2 * (384 + 2 * g + 64 * (c & 1) + (c >> 1)), a4 = kc + 2 * (512 + g + 32 * c);
#pragma unroll
    for (int r = 0; r < 2; r++) {
      sts32(a0 + 128 * r, pack_bf(k[0][2 * r], k[0][2 * r + 1]));
      sts32(a0 + 128 * r + 256, pack_bf(k[1][2 * r], k[1][2 * r + 1]));
      const uint32_t w2 = pack_bf(k[2][2 * r], k[2][2 * r + 1]);
      const uint32_t w3 = pack_bf(k[3][2 * r], k[3][2 * r + 1]);
      const uint32_t w4 = pack_bf(k[4][2 * r], k[4][2 * r + 1]);
      sts16(a2 + 64 * r, w2); sts16(a2 + 64 * r + 128, w2 >> 16);
      sts16(a3 + 32 * r, w3); sts16(a3 + 32 * r + 64, w3 >> 16);
      sts16(a4 + 16 * r, w4); sts16(a4 + 16 * r + 32, w4 >> 16);
    }
  }
  if (lane == 0) { sts16(kc + 2 * 640, pack_bf(k2048, 0.f)); sts32(kc - 4, 0); }
  __syncwarp();
  const uint32_t td = tb + T_D + 32;
#pragma unroll
  for (int hf = 0; hf < 2; hf++) {
    const uint2 v = lds64(kc + 256 * hf + 8 * lane);
    const uint32_t pv = lds32(kc + 256 * hf + 8 * lane - 4);
    sts128(td + 512 * hf + 16 * lane, __byte_perm(v.x, pv, 0x7610), __byte_perm(v.x, v.x, 0x1032), __byte_perm(v.y, v.x, 0x7610),
           __byte_perm(v.y, v.y, 0x1032));
  }
#pragma unroll
  for (int hf = 0; hf < 2; hf++) {
    const uint32_t v = lds32(kc + 512 + 128 * hf + 4 * lane), nx = lds32(kc + 516 + 128 * hf + 4 * lane);
    uint32_t w0 = __byte_perm(v, v, 0x1010);
    const uint32_t w1 = w0;
    if (hf == 0) { const uint32_t pv = lds32(kc + 508); if (lane == 0) w0 = __byte_perm(v, pv, 0x7610); }
    sts128(td + 1024 + 512 * hf + 16 * lane, w0, w1, __byte_perm(v, v, 0x1032), __byte_perm(nx, v, 0x7610));
  }
  {
    const uint32_t kk = lds16(kc + 2 * 384);
    const uint32_t w = lane < 3 ? (kk | (kk << 16)) : (lane == 3 ? (kk << 16) : 0u);
    if (lane < 24) sts32(td + 4 * (lane < 16 ? 512 + lane : lane - 24), w);
    const uint32_t lo_ = lds16(kc + 2 * 511), le_ = lds16(kc + 2 * 512);
    const uint32_t ja = tb + T_5 + (lane < 16 ? 4 * lane : 256 + 4 * lane);
    sts32(ja, lane == 16 ? (le_ << 16) : 0u);
    sts32(ja + 384, lane == 16 ? (lo_ << 16) : 0u);
    sts32(tb + (lane < 16 ? T_7 : T_9 - 64) + 4 * lane, 0u);
  }
#pragma unroll
  for (int s = 0; s < 2; s++) {
    const uint32_t b = kc + 2 * (s ? 512 : 384) + 8 * lane;
    const uint2 v = lds64(b);
    uint32_t em = lds16(b - 2), e0 = v.x;
    const uint32_t e4 = lds16(b + 8);
    if (lane == 0) { em = 0; e0 = 0; }
    sts64(tb + (s ? T_7 : T_3) + 64 + 8 * lane, __byte_perm(v.x, em, 0x5432), __byte_perm(v.y, v.x, 0x7632));
    sts64(tb + (s ? T_9 : T_5) + 64 + 8 * lane, __byte_perm(v.y, e0, 0x5410), __byte_perm(e4, v.y, 0x5410));
  }
  __syncwarp();
}

__device__ __forceinline__ uint32_t box2w(int lo, int n, int o) {
  return ((unsigned)(o - lo) < (unsigned)n ? 0x3F80u : 0u) | ((unsigned)(o + 1 - lo) < (unsigned)n ? 0x3F800000u : 0u);
}

__device__ __forceinline__ void conv_channel(uint32_t ub, uint32_t tb, int lane, uint4* ydst) {
  const int g = lane >> 2, c = lane & 3, x = g - 2 * c;
  const int mi = lane >> 3;
  const uint32_t qa = ub + U_PAD + 16 * (lane & 7) + ((mi == 0 || mi == 3) ? U_ODD : 0) - (mi == 0 ? 16 : 0);
  const uint32_t hb = ub + U_PAD + (mi & 1) * U_ODD + 16 * ((lane >> 4) + (lane & 7)) - 16;
  const uint32_t kv = lds16(tb + T_KC + 16 + 2 * 512);
  const int oh = c < 2 ? 8 + 2 * c : 2 * c - 8, og = c < 3 ? 2 * c : -10;
  uint32_t bx[4] = {box2w(g - 4, 9, 2 * c), box2w(g - 3, 7, 2 * c), box2w(g - 4, 9, oh), box2w(g - 3, 7, oh)};
  uint32_t by[4] = {box2w(g - 10, 5, 2 * c - 8), box2w(g - 5, 3, 2 * c - 8), box2w(g - 10, 5, og), box2w(g - 5, 3, og)};
  uint32_t lb0 = ((unsigned)(x + 5) < 2u ? kv : 0u) | ((unsigned)(x + 4) < 2u ? kv << 16 : 0u);
  uint32_t lb1 = ((unsigned)(x - 3) < 2u ? kv : 0u) | ((unsigned)(x - 4) < 2u ? kv << 16 : 0u);
  const int q0 = g - 1, q1 = c < 3 ? g : g - 2;
  uint32_t y0a = ub + U_PAD + (q0 & 1) * U_ODD + 16 * (q0 >> 1) + 4 * c;
  uint32_t y1a = ub + U_PAD + (q1 & 1) * U_ODD + 16 * (q1 >> 1) + 4 * c;
#pragma unroll
  for (int i = 0; i < 4; i++) asm volatile("" : "+r"(bx[i]), "+r"(by[i]));
  asm volatile("" : "+r"(lb0), "+r"(lb1), "+r"(y0a), "+r"(y1a));
  nb_sync(NB_GATE, 256);
  mbar_wait(BAR(MB_UFULL));
  mbar_spin(BAR(MB_EMPTY + 15));
  TS(36);
  float acc[16][4];
  {
    uint32_t z09[8], z07[8], zm9[8], zm7[8];
#pragma unroll
    for (int i = 0; i < 8; i++) {
      uint32_t h[4];
      ldsm4(h, hb + 128 * i);
      float y0, y1, y2, y3, w0, w1, w2, w3;
      mma0(y0, y1, y2, y3, bx[0], bx[1], bx[2], bx[3], h[2], c < 2 ? h[3] : h[1]);
      mma0(w0, w1, w2, w3, bx[0], bx[1], bx[2], bx[3], h[1], c < 2 ? h[2] : h[0]);
      z09[i] = pack_bf(y0, y1); z07[i] = pack_bf(y2, y3);
      zm9[i] = pack_bf(w0, w1); zm7[i] = pack_bf(w2, w3);
    }
  uint32_t f3[3][4][4];
  {
    const uint32_t fa = tb + T_7 + 4 * (16 + x);
#pragma unroll
    for (int tt = 0; tt < 3; tt++)
#pragma unroll
      for (int D = 0; D < 4; D++) {
        const uint32_t a = fa + (tt == 0 ? 316 : (tt == 1 ? 320 : 0)) + 64 * D;
        f3[tt][D][0] = lds32(a); f3[tt][D][1] = lds32(a + 32); f3[tt][D][2] = lds32(a - 32); f3[tt][D][3] = lds32(a);
      }
  }
    float a[4][2][4];
#pragma unroll
    for (int kap = 0; kap < 4; kap++)
#pragma unroll
      for (int sg = 0; sg < 2; sg++)
#pragma unroll
        for (int bk = 3; bk >= kap; bk--) {
          const uint32_t(&q0_)[4] = f3[sg ? 2 : 0][bk - kap];
          const uint32_t(&q1_)[4] = f3[sg ? 2 : 1][bk - kap];
          float(&a0)[4] = a[bk][0];
          float(&a1)[4] = a[bk][1];
          if (sg == 0 && kap == 0) {
            mma0(a0[0], a0[1], a0[2], a0[3], q0_[0], q0_[1], q0_[2], q0_[3], z09[0], z09[1]);
            mma0(a1[0], a1[1], a1[2], a1[3], q1_[0], q1_[1], q1_[2], q1_[3], zm9[0], zm9[1]);
          } else {
            mma(a0[0], a0[1], a0[2], a0[3], q0_[0], q0_[1], q0_[2], q0_[3], sg ? zm7[2 * kap] : z09[2 * kap], sg ? zm7[2 * kap + 1] : z09[2 * kap + 1]);
            mma(a1[0], a1[1], a1[2], a1[3], q1_[0], q1_[1], q1_[2], q1_[3], sg ? z07[2 * kap] : zm9[2 * kap], sg ? z07[2 * kap + 1] : zm9[2 * kap + 1]);
          }
        }
    SPLIT();
#pragma unroll
    for (int i = 0; i < 8; i++) {
      uint32_t h[4];
      ldsm4(h, qa + 128 * i);
      const float ci[4] = {a[i >> 1][0][2 * (i & 1)], a[i >> 1][0][2 * (i & 1) + 1], a[i >> 1][1][2 * (i & 1)], a[i >> 1][1][2 * (i & 1) + 1]};
      mmac(acc[8 + i], h[0], h[1], h[2], h[3], lb0, lb1, ci);
    }
  }
  TS(44);
  {
    uint2 a5[10], a3[10];
    const uint32_t aa = tb + T_5 + 4 * (8 + 2 * g - 2 * c);
#pragma unroll
    for (int m = 0; m < 10; m++) { a5[m] = lds64(aa + 32 * m); a3[m] = lds64(aa + 384 + 32 * m); }
    uint32_t x5[12][2], x3[12][2];
    auto ygen = [&](int kap) {
#pragma unroll
      for (int hh = 0; hh < 2; hh++) {
        float y0, y1, y2, y3;
        mma0(y0, y1, y2, y3, by[0], by[1], by[2], by[3], lds32(y0a + 128 * kap + 64 * hh), lds32(y1a + 128 * kap + 64 * hh));
        x5[kap][hh] = pack_bf(y0, y1);
        x3[kap][hh] = pack_bf(y2, y3);
      }
    };
    ygen(11); ygen(10); ygen(9); ygen(8);
#pragma unroll
    for (int kap = 11; kap >= 0; kap--) {
      if (kap >= 4) ygen(kap - 4);
#pragma unroll
      for (int sg = 0; sg < 2; sg++)
#pragma unroll
        for (int i = 4; i >= 0; i--) {
          const int be = kap + 4 + i;
          if (be <= 15) {
            const uint2 &hi = sg ? a3[2 * i + 1] : a5[2 * i + 1], &lo = sg ? a3[2 * i] : a5[2 * i];
            const uint32_t b0 = sg ? x3[kap][0] : x5[kap][0], b1 = sg ? x3[kap][1] : x5[kap][1];
            if (be < 8 && i == 0 && sg == 0) mma0(acc[be][0], acc[be][1], acc[be][2], acc[be][3], hi.x, hi.y, lo.x, lo.y, b0, b1);
            else mma(acc[be][0], acc[be][1], acc[be][2], acc[be][3], hi.x, hi.y, lo.x, lo.y, b0, b1);
          }
        }
    }
  }
  TS(45);
  {
    const uint32_t st = tb + T_ST + lane * 8;
#pragma unroll
    for (int be = 4; be < 12; be++) sts64(st + 256 * be, pack_bf(acc[be][0], acc[be][1]), pack_bf(acc[be][2], acc[be][3]));
    SPLIT();
    uint32_t F[66], qd[8][4];
    const uint32_t fa = tb + T_D + 32 + 4 * x;
#pragma unroll
    for (int i = 0; i < 32; i++) {
      const int s = 120 - (i >> 2) - 8 * (i & 3);
      uint32_t(&q)[4] = qd[i & 7];
      ldsm4(q, qa + 16 * s);
      const int m = 16 * (i & 3) + 2 * (i >> 2);
      F[m] = lds32(fa + 32 * m); F[m + 1] = lds32(fa + 32 * m + 32);
#pragma unroll
      for (int be = 15; be >= 12; be--) {
        const int de = 8 * be - s;
        float(&a)[4] = (be >= 14 && !(i & 1)) ? acc[be - 4] : acc[be];
        if (de >= 0 && be >= 14 && i == 2 * (15 - be)) mma0(a[0], a[1], a[2], a[3], q[0], q[1], q[2], q[3], F[2 * de + 1], F[2 * de]);
        else if (de >= 0) mma(a[0], a[1], a[2], a[3], q[0], q[1], q[2], q[3], F[2 * de + 1], F[2 * de]);
      }
    }
#pragma unroll
    for (int i = 0; i < 8; i++) acc[14 + (i >> 2)][i & 3] += acc[10 + (i >> 2)][i & 3];
    F[64] = lds32(fa + 32 * 64); F[65] = lds32(fa + 32 * 65);
#pragma unroll
    for (int i = 0; i < 6; i++) ldsm4(qd[i], qa + 128 * 11 - 16 * i);
    uint2 sv = lds64(st + 256 * 11);
    float ci[4] = {bf_lo(sv.x), bf_hi(sv.x), bf_lo(sv.y), bf_hi(sv.y)};
    float T[5][4];
#pragma unroll
    for (int i = 0; i < 16; i++) T[i >> 2][i & 3] = acc[12 + (i >> 2)][i & 3];
    nb_sync(NB_YZ, 160);
    TS(46);
    uint32_t held[2];
#pragma unroll
    for (int be = 11; be >= 0; be--) {
      if (be & 1) SPLITN(be);
      const uint32_t qp = qa + 128 * be;
#pragma unroll
      for (int k = 4; k >= 1; k--) mmac(T[k], qd[0][0], qd[0][1], qd[0][2], qd[0][3], F[16 * k + 1], F[16 * k], T[k - 1]);
      if (be >= 4) mmac(T[0], qd[0][0], qd[0][1], qd[0][2], qd[0][3], F[1], F[0], ci);
      else mma0(T[0][0], T[0][1], T[0][2], T[0][3], qd[0][0], qd[0][1], qd[0][2], qd[0][3], F[1], F[0]);
      ldsm4(qd[6], qp - 16 * 6);
      ldsm4(qd[7], qp - 16 * 7);
      if (be > 4) sv = lds64(st + 256 * (be - 1));
#pragma unroll
      for (int i = 1; i < 8; i++) {
#pragma unroll
        for (int k = 3; k >= 0; k--)
          mma(T[k][0], T[k][1], T[k][2], T[k][3], qd[i][0], qd[i][1], qd[i][2], qd[i][3], F[16 * k + 2 * i + 1], F[16 * k + 2 * i]);
        if (i < 7 && be > 0) ldsm4(qd[i - 1], qp - 128 - 16 * (i - 1));
        if (i == 2) {
          const uint32_t w0 = pack_bf(T[4][0], T[4][1]), w1 = pack_bf(T[4][2], T[4][3]);
          if (be & 1) { held[0] = w0; held[1] = w1; }
          else st_x(ydst + (be + 4) * 16, nz(w0), w1, held[0], held[1]);
          if ((be & 3) == 3 && be < 11) nb_arrive(NB_Y + 2 + (be >> 2), 160);
        }
        if (i == 4 && be > 4) { ci[0] = bf_lo(sv.x); ci[1] = bf_hi(sv.x); ci[2] = bf_lo(sv.y); ci[3] = bf_hi(sv.y); }
      }
    }
    nb_arrive(NB_Y + 1, 160);
#pragma unroll
    for (int B = 1; B >= 0; B--)
      st_x(ydst + B * 32, nz(pack_bf(T[2 * B][0], T[2 * B][1])), pack_bf(T[2 * B][2], T[2 * B][3]),
           pack_bf(T[2 * B + 1][0], T[2 * B + 1][1]), pack_bf(T[2 * B + 1][2], T[2 * B + 1][3]));
  }
}

__device__ __forceinline__ void dual_exp(const uint32_t* w, uint32_t* e) {
  const float L = 1.44268798828125f;
  uint32_t mx = bmax2(bmax2(w[0], w[1]), bmax2(w[2], w[3]));
  uint32_t mn = bmin2(bmin2(w[0], w[1]), bmin2(w[2], w[3]));
  mx = bmax2(mx, __shfl_xor_sync(0xffffffffu, mx, 1));
  mn = bmin2(mn, __shfl_xor_sync(0xffffffffu, mn, 1));
  mx = bmax2(mx, __shfl_xor_sync(0xffffffffu, mx, 2));
  mn = bmin2(mn, __shfl_xor_sync(0xffffffffu, mn, 2));
  const float mx0 = bf_lo(mx) * -L, mx1 = bf_hi(mx) * -L, mn0 = bf_lo(mn) * L, mn1 = bf_hi(mn) * L;
#pragma unroll
  for (int i = 0; i < 2; i++) {
    const float a0 = bf_lo(w[2 * i]), a1 = bf_hi(w[2 * i]), b0 = bf_lo(w[2 * i + 1]), b1 = bf_hi(w[2 * i + 1]);
    e[2 * i] = pack_bf(ex2(fmaf(a0, L, mx0)), ex2(fmaf(b0, L, mx0)));
    e[2 * i + 1] = pack_bf(ex2(fmaf(a1, L, mx1)), ex2(fmaf(b1, L, mx1)));
    e[4 + 2 * i] = pack_bf(ex2(fmaf(a0, -L, mn0)), ex2(fmaf(b0, -L, mn0)));
    e[5 + 2 * i] = pack_bf(ex2(fmaf(a1, -L, mn1)), ex2(fmaf(b1, -L, mn1)));
  }
}
__device__ __forceinline__ void normalise(uint32_t* e, const float (&s)[4]) {
  const uint32_t r = pack_bf(rcp(s[0]), rcp(s[2]));
  const __nv_bfloat162 rr = *(const __nv_bfloat162*)&r;
#pragma unroll
  for (int i = 0; i < 4; i++) {
    const __nv_bfloat162 v = __hmul2(*(const __nv_bfloat162*)&e[i], (i & 1) ? __high2bfloat162(rr) : __low2bfloat162(rr));
    e[i] = *(const uint32_t*)&v;
  }
}
__host__ __device__ constexpr uint64_t qdesc(uint32_t addr) { return mkdesc(addr, 128, 256, 0); }

__global__ void __launch_bounds__(NTHREADS, 1)
fused_kernel(const Params P, const __grid_constant__ CUtensorMap mx, const __grid_constant__ CUtensorMap mw,
             const __grid_constant__ CUtensorMap mo, const __grid_constant__ CUtensorMap mu,
             const __grid_constant__ CUtensorMap mout) {
  constexpr uint32_t sb = SB;
  const int tid = threadIdx.x, lane = tid & 31;
  const int warp = __shfl_sync(0xffffffffu, tid >> 5, 0);
  const int b = blockIdx.x, oct = b >> 3, i8 = b & 7;
  const int rt = (((oct & 4) ? ~oct : oct) & 3) * 2 + (i8 >> 2);
  const int hp = (oct >> 2) * 4 + (i8 & 3);

  const int wg = warp >> 2, w = warp & 3;
  const int d = b * 4 + ((tid >> 5) & 3);
  const KgenRaw raw = kgen_load(P, d, (tid >> 7) & 1, lane, (tid + 128) & 256);
  const uint32_t tb = sb + OFF_T + w * T_CH;
  if (warp >= 12) {
    asm volatile("setmaxnreg.dec.sync.aligned.u32 32;");
    if (warp == 12) {
      if (lane == 0) {
#pragma unroll
        for (int i = 0; i < 9; i++) mbar_init(BAR(i), 1);
        asm volatile("fence.mbarrier_init.release.cluster;" ::: "memory");
      }
      __syncwarp();
      if (lane < 9) mbar_expect(BAR(0) + 8 * lane, lane == 0 ? 16384 : 28672);
      __syncwarp();
      nb_arrive(NB_PROD, 512);
#pragma unroll 1
      for (int kb = 0; kb < 8; kb++) {
        if (kb == U_AT) e_tma4d(sb + OFF_STG0, &mu, BAR(MB_URAW), i8 * 64, oct * 2);
        e_tma3d(sb + OFF_W + kb * 12288, &mw, BAR(MB_FULL) + 8 * kb, hp * 32, kb * 64, 0);
        if (kb < 5) e_tma2d(sb + OFF_X + (kb < 2 ? kb + 3 : kb - 2) * 16384, &mx, BAR(MB_FULL) + 8 * kb, kb * 64, rt * 256);
      }
      if (smem_u32(smem_raw) != SB) __trap();
      if (lane == 0) TS1(54);
      nb_sync(NB_GATE + 1, 64);
      e_prefetch(P.u + (size_t)b * 8192, 16384);
      e_prefetch(P.x + (size_t)(rt * 256 + 128 + hp * 8) * 512, 8192);
      uint32_t slot = sb + OFF_X + 3 * 16384;
#pragma unroll 1
      for (int n = 0; n < 11; n++) {
        mbar_spin(BAR(MB_EMPTY) + 8 * n);
        const int m = n + 5;
        e_tma2d(slot, &mx, BAR(MB_FULL) + 8 * m, (m & 7) * 64, rt * 256 + (m >> 3) * 128);
        slot = slot == sb + OFF_X + 4 * 16384 ? sb + OFF_X : slot + 16384;
        if (n == U_AT - 8) e_tma4d(sb + OFF_STG0, &mu, BAR(MB_URAW), i8 * 64, oct * 2);
        if (n == 7) {
          e_prefetch(P.wo + (size_t)b * 2048, 4096);
          asm volatile("prefetch.tensormap [%0];" ::"l"(&mo) : "memory");
          asm volatile("prefetch.tensormap [%0];" ::"l"(&mout) : "memory");
        }
      }
#pragma unroll 1
      for (int i = 0; i < 8; i++) {
        mbar_wait(BAR(MB_EMPTY + 10) + 8 * ((0x54332222u >> (4 * i)) & 7));
        const int w0 = (0x54736210u >> (4 * i)) & 7;
        e_tma3d(sb + OFF_W + w0 * 16384, &mo, BAR(MB_WO), 0, w0 * 64, (hp & 3) * 2);
      }
    } else {
      if (warp == 13) {
        if (lane == 0) {
#pragma unroll
          for (int i = 9; i < 40; i++) mbar_init(BAR(i), i < MB_EMPTY ? 1 : 4);
          asm volatile("fence.mbarrier_init.release.cluster;" ::: "memory");
        }
        __syncwarp();
        if (lane < 14 && lane != 9) mbar_expect(BAR(MB_FULL + 8) + 8 * lane, lane == 8 ? 131072 : (lane == 10 ? 8192 : (lane == 13 ? 24576 : 16384)));
        nb_arrive(NB_GATE + 1, 64);
      } else if (warp == 14) {
        asm volatile("prefetch.tensormap [%0];" ::"l"(&mw) : "memory");
        asm volatile("prefetch.tensormap [%0];" ::"l"(&mx) : "memory");
        asm volatile("prefetch.tensormap [%0];" ::"l"(&mu) : "memory");
        e_prefetch(P.x + (size_t)(rt * 256 + hp * 8) * 512, 8192);
      }
      nb_sync(NB_PROD, 512);
      if (warp == 15) {
        const uint4 v0 = __ldg((const uint4*)P.wphi + hp * 64 + lane), v1 = __ldg((const uint4*)P.wphi + hp * 64 + 32 + lane);
        sts128(sb + OFF_PHI + (lane & 1) * 256 + (lane >> 1) * 16, v0.x, v0.y, v0.z, v0.w);
        sts128(sb + OFF_PHI + 512 + (lane & 1) * 256 + (lane >> 1) * 16, v1.x, v1.y, v1.z, v1.w);
        const uint32_t one = (((lane >> 3) ^ (lane >> 4)) & 1) ? 0u : ((lane & 1) ? 0x3F800000u : 0x3F80u);
        const int q = (lane >> 1) & 3;
        sts128(sb + OFF_EYE + lane * 16, q == 0 ? one : 0u, q == 1 ? one : 0u, q == 2 ? one : 0u, q == 3 ? one : 0u);
        sts64(sb + OFF_ONE + lane * 8, 0x3F803F80u, 0x3F803F80u);
        asm volatile("fence.proxy.async.shared::cta;" ::: "memory");
        nb_arrive(NB_KREAD, 160);
      }
      uint32_t* cnt = (uint32_t*)(P.xs + X_CNT) + (warp == 13 ? i8 : (warp == 14 ? 8 + rt : 16 + oct)) * 32;
      const unsigned target = (ld_x32(cnt) & ~15u) + 16;
      if (warp != 14) {
        if (warp == 15) mbar_wait(BAR(MB_EMPTY + ZERO_STEP));
        uint4* pz = P.xs + (warp == 13 ? X_PART + (hp * 8 + rt) * 144 : X_Y + b * 1024) + lane;
#pragma unroll 1
        for (int i = (warp == 13 ? 144 : 1024) - lane; i > 0; i -= 32, pz += 32) st_x(pz, 0, 0, 0, 0);
      }
      if (warp == 15) __syncwarp();
      else nb_sync(warp == 13 ? NB_INIT : NB_ODONE, warp == 13 ? 160 : 288);
      if (lane == 0) asm volatile("red.release.gpu.global.add.u32 [%0], %1;" ::"l"(cnt), "r"(warp == 15 ? 2 : 1) : "memory");
      if (lane == 0) TS1(warp == 13 ? 50 : (warp == 14 ? 57 : 53));
      __syncwarp();
      if (warp == 14) nb_arrive(NB_GATE + 1, 160);
      asm volatile("fence.proxy.async.shared::cta;" ::: "memory");
      if (warp == 13) cnt += ((lane & 1 ? b >> 4 : i8 ^ (lane & 4)) - i8) * 32;
#pragma unroll 1
      for (int i = 0; i < SPIN_MAX; i++) {
        unsigned v;
        asm volatile("ld.acquire.gpu.global.u32 %0, [%1];" : "=r"(v) : "l"(cnt) : "memory");
        if (__all_sync(0xffffffffu, (int)(v - target) >= 0)) break;
      }
      if (lane == 0) TS1(warp == 13 ? 51 : (warp == 14 ? 58 : 55));
      if (warp == 15) { nb_arrive(NB_YZ, 160); return; }
      asm volatile("fence.proxy.async.global;" ::: "memory");
      if (warp == 13) {
        mbar_wait(BAR(MB_EMPTY + 11));
        e_expect(BAR(MB_UFULL), 4 * U_CH);
        e_bulk(sb + OFF_U, P.xs + X_UT + b * (U_CH / 4), 4 * U_CH, BAR(MB_UFULL));
      } else {
        const uint4* src = P.xs + X_O + (rt * 4 + (hp >> 2)) * 4096;
        e_bulk(sb + OFF_X + 32768 + 57344, src + 3584, 8192, BAR(MB_O));
        e_bulk(sb + OFF_X + 32768, src, 16384, BAR(MB_O + 1));
        e_bulk(sb + OFF_X + 49152, src + 1024, 16384, BAR(MB_O + 2));
        e_bulk(sb + OFF_STG0, src + 3200, 6144, BAR(MB_O + 3));
        nb_sync(NB_BDONE, 288);
        asm volatile("fence.proxy.async.shared::cta;" ::: "memory");
        e_bulk(sb + OFF_U, src + 2048, 18432, BAR(MB_O + 3));
      }
    }
    return;
  }

  asm volatile("setmaxnreg.inc.sync.aligned.u32 160;");
  const int t = tid & 127;
  const int g = lane >> 2, c = lane & 3;
  const uint32_t kp = ((tb + 127) & ~127u) + (wg & 1) * 2048;
  const KgenAddr kad = kgen_addr(lane, kp);
  if (wg) nb_sync(NB_PROD, 512);
  float k[5][4], k2048, ksc;
  if (wg) {
    KgenOps op;
    kgen_unit(raw, kad, blockIdx.y, op, k2048, ksc);
    TS(40 + wg);
    if (wg == 1) {
      mbar_wait(BAR(MB_URAW));
      TS(48);
      uint4* dst = P.xs + X_UT + (i8 * 64 + g) * (U_CH / 16) + (w & 1) * (U_ODD / 16) + U_PAD / 16 + oct * 8 + (w >> 1) * 4 + c;
      const int ln = ((lane >> 1) & 3) + 4 * (lane & 1);
      const uint32_t src = sb + OFF_STG0 + w * 4096 + ((lane >> 3) * 8 + ln) * 128;
#pragma unroll 1
      for (int hf = 0; hf < 8; hf += 4) {
        uint32_t r[4][4];
#pragma unroll
        for (int i = 0; i < 4; i++) ldsm4t(r[i], src + (((hf + i) ^ ln) << 4));
#pragma unroll
        for (int i = 0; i < 4; i++) dst[(hf + i) * (U_CH / 2)] = make_uint4(r[i][0], r[i][1], r[i][2], r[i][3]);
      }
      nb_arrive(NB_INIT, 160);
      if (lane == 0) mbar_arrive(BAR(MB_AUX));
      TS(30);
    }
    mbar_wait(BAR(MB_EMPTY + 5));
    mbar_spin(BAR(MB_EMPTY + 7));
    kgen_burst(op, k);
    if (wg == 1) {
      uint32_t h[10];
#pragma unroll
      for (int j = 0; j < 10; j++) h[j] = hu(__floats2half2_rn(k[j >> 1][2 * (j & 1)], k[j >> 1][2 * (j & 1) + 1]));
      sts128(kp + lane * 16, h[0], h[1], h[2], h[3]);
      sts128(kp + 512 + lane * 16, h[4], h[5], h[6], h[7]);
      sts128(kp + 1024 + lane * 16, h[8], h[9], fu(k2048), fu(ksc));
    } else if ((fu(k[0][0]) & fu(k[1][0]) & fu(k[2][0]) & fu(k[3][0]) & fu(k[4][0])) == 0xffffffffu) {
      sts32(kp, 0);
    }
    nb_sync(NB_PREP, 256);
  } else {
    nb_sync(NB_PROD, 512);
  }
  {
    if (wg == 2) {
#pragma unroll
      for (int j = 0; j < 5; j++) { k[j][0] *= ksc; k[j][1] *= ksc; k[j][2] *= ksc; k[j][3] *= ksc; }
      const unsigned short dsk = __ldg((const unsigned short*)P.Dskip + d);
      {
        const uint32_t src = kp + 2048 + lane * 16;
        const uint4 v0 = lds128(src), v1 = lds128(src + 512), v2 = lds128(src + 1024);
        const uint32_t h[10] = {v0.x, v0.y, v0.z, v0.w, v1.x, v1.y, v1.z, v1.w, v2.x, v2.y};
#pragma unroll
        for (int j = 0; j < 10; j++) {
          const float2 f = __half22float2(*(const __half2*)&h[j]);
          k[j >> 1][2 * (j & 1)] = fmaf(f.x, uf(v2.w), k[j >> 1][2 * (j & 1)]);
          k[j >> 1][2 * (j & 1) + 1] = fmaf(f.y, uf(v2.w), k[j >> 1][2 * (j & 1) + 1]);
        }
        k2048 += uf(v2.z);
      }
#pragma unroll
      for (int o2 = 16; o2; o2 >>= 1) k2048 += __shfl_xor_sync(0xffffffffu, k2048, o2);
      if (lane == 0) k[0][0] += bf_lo(dsk);
      __syncwarp();
      TS(34);
      build_tables(tb, lane, k, k2048);
      TS(35);
      uint4* const g_y = P.xs + X_Y;
      conv_channel(sb + OFF_U + w * U_CH, tb, lane, g_y + (size_t)d * 256 + lane);
      nb_arrive(NB_BDONE, 288);
      nb_arrive(NB_Y, 160);
      TS(37);
      if (w == 0) TSDUMP(32);
      return;
    }
    TS(wg * 16 + 1);
  }

  float acc[2][48];
  {
    uint32_t fb = BAR(MB_FULL) + 64 * wg;
    uint32_t da = (uint32_t)mkdesc(sb + OFF_X, 16, 0, 0) + (wg ? 1024 : 3072), db = (uint32_t)mkdesc(sb + OFF_W, 4096, 0, 0);
    constexpr uint64_t ha = mkdesc(0, 0, 1024, 1), hb = mkdesc(0, 0, 512, 2);
    mbar_spin(fb);
    TS(wg * 16 + 2);
#pragma unroll 1
    for (int kb = 0; kb < 8; kb++) {
      WG_FENCE();
#pragma unroll
      for (int k = 0; k < 4; k++) {
        wgmma_ss_n96(acc[0], ha | (da + 2 * k), hb | (db + 64 * k), k ? 1 : kb);
        wgmma_ss_n96(acc[1], ha | (da + 2 * k + 512), hb | (db + 64 * k), k ? 1 : kb);
      }
      WG_COMMIT();
      if (kb < 7) mbar_spin(fb + 8);
      WG_WAIT(1);
      if (kb > 0) e_arrive(fb + 8 * (MB_EMPTY - MB_FULL - 1));
      fb += 8; db += 768;
      da = da == (uint32_t)mkdesc(sb + OFF_X + 65536, 16, 0, 0) ? da - 4096 : da + 1024;
    }
    if (wg == 0) nb_sync(NB_KREAD, 160);
    WG_WAIT(0);
    e_arrive(fb + 8 * (MB_EMPTY - MB_FULL - 1));
    SPLIT();
  }
  TS(wg * 16 + 3);

  constexpr uint32_t stg0 = sb + OFF_STG0, stg1 = sb + OFF_X + 32768;
  uint4* const g_part = P.xs + X_PART;
  uint4* const g_o = P.xs + X_O;
  constexpr uint32_t kvs = stg0;
  auto pack8 = [](const float* a) { return make_uint4(pack_bf(a[0], a[1]), pack_bf(a[2], a[3]), pack_bf(a[4], a[5]), pack_bf(a[6], a[7])); };
  auto feat = [&](const uint4 (&af)[4], float (&p)[4][8]) {
    WG_FENCE();
#pragma unroll
    for (int u = 0; u < 4; u++) wgmma_rs_n16(p[u], af[u], qdesc(sb + OFF_PHI + (u & 1) * 512), 0);
    WG_COMMIT();
  };
  auto packp = [](const float (&p)[4][8], uint32_t (&pw)[16]) {
#pragma unroll
    for (int i = 0; i < 16; i++) pw[i] = pack_bf(p[i >> 2][(i & 1) + 2 * (i & 2)], p[i >> 2][(i & 1) + 2 * (i & 2) + 2]);
  };
  auto contract = [&](float (&kc)[20], uint32_t stg, int acc_in) {
    WG_FENCE();
#pragma unroll
    for (int s = 0; s < 8; s++) wgmma_ss_n40(kc, qdesc(stg + s * SLAB), qdesc(stg + s * SLAB + 2048), s ? 1 : acc_in);
    WG_COMMIT();
    WG_WAIT(0);
  };
  uint32_t eq[32];
  {
    uint4 af[4], aq[4], vp[4];
    float p[4][8];
#pragma unroll
    for (int u = 0; u < 4; u++) af[u] = pack8(acc[u >> 1] + 16 + 8 * (u & 1));
    feat(af, p);
#pragma unroll
    for (int u = 0; u < 4; u++) { aq[u] = pack8(acc[u >> 1] + 8 * (u & 1)); vp[u] = pack8(acc[u >> 1] + 32 + 8 * (u & 1)); }
    WG_WAIT(0);
    uint32_t pw[16], ek[32];
    packp(p, pw);
#pragma unroll
    for (int u = 0; u < 4; u++) dual_exp(pw + 4 * u, ek + 8 * u);
    TS(wg * 16 + 12);
    mbar_spin(wg ? BAR(MB_EMPTY + 15) : BAR(MB_AUX));
    float rs[8][4];
    WG_FENCE();
#pragma unroll
    for (int i = 0; i < 8; i++) wgmma_rs_n8(rs[i], make_uint4(ek[4 * i], ek[4 * i + 1], ek[4 * i + 2], ek[4 * i + 3]), qdesc(sb + OFF_ONE), 0);
    WG_COMMIT();
    feat(aq, p);
    const uint32_t sl = (wg ? stg1 : stg0) + w * SLAB + lane * 16;
#pragma unroll
    for (int i = 0; i < 4; i++) stsm4(sl + (i >> 1) * 4 * SLAB + 2048 + (i & 1) * 512, vp[i].x, vp[i].y, vp[i].z, vp[i].w);
    sts128(sl + (lane >> 4) * (4 * SLAB - 256) + 3072, 0x3F803F80u, 0x3F803F80u, 0x3F803F80u, 0x3F803F80u);
    WG_WAIT(1);
#pragma unroll
    for (int i = 0; i < 8; i++) {
      normalise(ek + 4 * i, rs[i]);
      stsm4(sl + (i >> 2) * 4 * SLAB + (i & 3) * 512, ek[4 * i], ek[4 * i + 1], ek[4 * i + 2], ek[4 * i + 3]);
    }
    asm volatile("fence.proxy.async.shared::cta;" ::: "memory");
    TS(wg * 16 + 13);
    if (wg) {
      nb_arrive(NB_ST0, 256);
      nb_arrive(NB_GATE, 256);
    } else {
      float kc[20];
      uint4* pp = g_part + (size_t)(hp * 8 + rt) * 144 + t;
      uint32_t* pz = (uint32_t*)(pp - t + 128) + w * 16 + c * 8 + g;
      asm volatile("" : "+l"(pp), "+l"(pz));
      nb_sync(NB_WG0, 128);
      contract(kc, stg0, 0);
      mbar_wait(BAR(MB_UFULL));
      TS(15);
      nb_sync(NB_ST0, 256);
      contract(kc, stg1, 1);
      TS(6);
      float kv[8];
#pragma unroll
      for (int i = 0; i < 8; i++) kv[i] = w & 2 ? kc[8 + i] : kc[i];
      st_x(pp, nz(pack_bf(kv[0], kv[1])), pack_bf(kv[2], kv[3]), pack_bf(kv[4], kv[5]), pack_bf(kv[6], kv[7]));
      if (c < 2) st_x32(pz, nz(fu(c ? kc[18] : kc[16])));
      TS(5);
    }
    SPLIT();
    WG_WAIT(0);
    packp(p, pw);
#pragma unroll
    for (int u = 0; u < 4; u++) dual_exp(pw + 4 * u, eq + 8 * u);
    SPLIT();
  }
  TS(wg * 16 + 4);
  if (wg == 1) {
    mbar_wait(BAR(MB_UFULL));
    const uint4* ps = g_part + (size_t)hp * 8 * 144 + t;
    const uint32_t* zs = (const uint32_t*)(g_part + (size_t)(hp * 8 + (lane >> 4) * 4) * 144 + 128) + w * 16 + (lane & 15);
    uint4 v[8];
    uint32_t zv[4];
#pragma unroll 1
    for (int it = 0; it < SPIN_MAX; it++) {
#pragma unroll
      for (int i = 0; i < 8; i++) v[i] = ld_x(ps + i * 144);
#pragma unroll
      for (int i = 0; i < 4; i++) zv[i] = ld_x32(zs + i * 576);
      uint32_t m = min(min(zv[0], zv[1]), min(zv[2], zv[3]));
#pragma unroll
      for (int i = 0; i < 8; i++) m = min(m, v[i].x);
      if (__all_sync(0xffffffffu, m != 0)) break;
    }
    float s[8];
    WG_FENCE();
#pragma unroll
    for (int r = 0; r < 8; r++) wgmma_rs_n16(s, v[r], qdesc(sb + OFF_EYE), r);
    WG_COMMIT();
    float zsum = (uf(zv[0]) + uf(zv[1])) + (uf(zv[2]) + uf(zv[3]));
    zsum += __shfl_xor_sync(0xffffffffu, zsum, 16);
    const uint32_t z1 = pack_bf(zsum, 1.f);
    if (lane < 16) sts128(kvs + w * 768 + 512 + lane * 16, z1, z1, z1, z1);
    WG_WAIT(0);
    stsm4(kvs + w * 768 + lane * 16, pack_bf(s[0], s[1]), pack_bf(s[2], s[3]), pack_bf(s[4], s[5]), pack_bf(s[6], s[7]));
    asm volatile("fence.proxy.async.shared::cta;" ::: "memory");
    TS(22);
  }
  nb_sync(NB_KV, 256);
  {
    float n[8][12];
    WG_FENCE();
#pragma unroll
    for (int i = 0; i < 8; i++) wgmma_rs_n24(n[i], make_uint4(eq[4 * i], eq[4 * i + 1], eq[4 * i + 2], eq[4 * i + 3]), qdesc(kvs + (i & 3) * 768), 0);
    WG_COMMIT();
    uint32_t* od = (uint32_t*)(g_o + (size_t)((rt * 4 + wg * 2) * 32 + hp * 2) * 128) + w * 64 + lane;
    WG_WAIT(0);
#pragma unroll
    for (int u = 0; u < 4; u++) {
      float(&np)[12] = n[2 * u];
      const float(&nm)[12] = n[2 * u + 1];
      const float q0 = np[9] * rcp(nm[9]), q1 = np[11] * rcp(nm[11]);
      const float r0 = rcp(fmaf(nm[8], q0, fmaf(np[9], 1e-6f, np[8]))), r1 = rcp(fmaf(nm[10], q1, fmaf(np[11], 1e-6f, np[10])));
#pragma unroll
      for (int i = 0; i < 8; i++) np[i] = fmaf(nm[i], (i & 2) ? q1 : q0, np[i]);
      uint32_t* o = od + (u >> 1) * 16384 + (u & 1) * 512;
      o[0] = pack_bf(np[0] * r0, np[1] * r0);
      o[32] = pack_bf(np[2] * r1, np[3] * r1);
      o[256] = pack_bf(np[4] * r0, np[5] * r0);
      o[288] = pack_bf(np[6] * r1, np[7] * r1);
      if (u == 1) SPLIT();
    }
  }
  TS(wg * 16 + 7);
  nb_arrive(NB_ODONE, 288);
  if (wg) {
    const uint4* src = P.xs + X_Y + (oct * 32 + c * 8) * 256 + (2 * w + (g >> 2)) * 32 + i8 * 4 + (g & 3);
    __nv_bfloat16* dst = P.out + (size_t)((2 * w + (g >> 2)) * 256 + i8 * 16 + (g & 3) * 2) * 1024 + 512 + oct * 32 + c * 8;
    nb_sync(NB_GATE + 1, 160);
    nb_sync(NB_Y + w, 160);
    uint4 v[8];
#pragma unroll 1
    for (int it = 0; it < SPIN_MAX; it++) {
      uint32_t m = 0xffffffffu;
#pragma unroll
      for (int i = 0; i < 8; i++) v[i] = ld_x(src + i * 256);
#pragma unroll
      for (int i = 0; i < 8; i++) m = min(m, v[i].x);
      if (__all_sync(0xffffffffu, m != 0)) break;
    }
#pragma unroll
    for (int i = 0; i < 8; i++) *(uint4*)(dst + (size_t)((i >> 2) * 128 + ((i >> 1) & 1) * 8 + (i & 1)) * 1024) = tr_row(v, i);
    TS(31);
    GT(63);
    if (w == 0) TSDUMP(16);
    return;
  }
  mbar_wait(BAR(MB_WO));
  nb_sync(NB_BDONE, 288);
  TS(8);
  mbar_spin(BAR(MB_O));
  TS(9);
  constexpr uint64_t ha = mkdesc(0, 0, 128, 0), hb = mkdesc(0, 0, 1024, 1);
  constexpr uint32_t da0 = (uint32_t)mkdesc(stg1, 1024, 0, 0), db0 = (uint32_t)mkdesc(sb + OFF_W, 8192, 0, 0);
  const uint32_t ot = ((sb + OFF_T + 1023) & ~1023u) + w * 4096;
  auto store_half = [&](const float* oc, int hf) {
#pragma unroll
    for (int i = 0; i < 8; i += 2)
      stsm4(ot + hf * 2048 + (lane & 15) * 128 + (((i + (lane >> 4)) ^ lane) & 7) * 16, pack_bf(oc[4 * i], oc[4 * i + 1]),
            pack_bf(oc[4 * i + 2], oc[4 * i + 3]), pack_bf(oc[4 * i + 4], oc[4 * i + 5]), pack_bf(oc[4 * i + 6], oc[4 * i + 7]));
    asm volatile("fence.proxy.async.shared::cta;" ::: "memory");
    __syncwarp();
    e_store2d(&mout, ot + hf * 2048, (hp & 3) * 128 + hf * 64, (rt * 4 + (hp >> 2)) * 64 + w * 16);
  };
  float oc[64];
#pragma unroll 1
  for (int j = 0; j < 8; j++) {
    const int kb = (j + 7) & 7;
    if ((j & 1) && j < 6) mbar_spin(BAR(MB_O + 1) + 4 * (j - 1));
    WG_FENCE();
#pragma unroll
    for (int k = 0; k < 4; k++) wgmma_ss_n128(oc, ha | (da0 + 512 * kb + 128 * k), hb | (db0 + 1024 * kb + 128 * k), k ? 1 : j);
    WG_COMMIT();
  }
  WG_WAIT(0);
  TS(10);
  store_half(oc, 0);
  store_half(oc + 32, 1);
  asm volatile(ELECT "cp.async.bulk.commit_group;\n@p cp.async.bulk.wait_group.read 0;\n}\n" ::: "memory");
  TS(wg * 16 + 11);
  GT(61 + wg);
  if (w == 0) TSDUMP(0);
  if (w == 1) TSDUMP(48);
}

typedef CUresult (*EncodeFn)(CUtensorMap*, CUtensorMapDataType, cuuint32_t, void*, const cuuint64_t*, const cuuint64_t*,
                             const cuuint32_t*, const cuuint32_t*, CUtensorMapInterleave, CUtensorMapSwizzle,
                             CUtensorMapL2promotion, CUtensorMapFloatOOBfill);

}

extern "C" void kernel_launch(void* const* d_in, const int* in_sizes, int n_in, void* d_out, int out_size) {
  (void)in_sizes; (void)n_in; (void)out_size;
  void* fn = nullptr;
  cudaDriverEntryPointQueryResult qr;
  cudaGetDriverEntryPoint("cuTensorMapEncodeTiled", &fn, cudaEnableDefault, &qr);
  EncodeFn enc = (EncodeFn)fn;
  CUtensorMap mx, mw, mo, mu, mout;
  const cuuint32_t es[5] = {1, 1, 1, 1, 1};
  {
    cuuint64_t dims[2] = {512, 2048}, st[1] = {1024};
    cuuint32_t box[2] = {64, 128};
    enc(&mx, CU_TENSOR_MAP_DATA_TYPE_BFLOAT16, 2, d_in[0], dims, st, box, es, CU_TENSOR_MAP_INTERLEAVE_NONE,
        CU_TENSOR_MAP_SWIZZLE_128B, CU_TENSOR_MAP_L2_PROMOTION_L2_128B, CU_TENSOR_MAP_FLOAT_OOB_FILL_NONE);
  }
  {
    cuuint64_t dims[3] = {512, 512, 3}, st[2] = {3072, 1024};
    cuuint32_t box[3] = {32, 64, 3};
    enc(&mw, CU_TENSOR_MAP_DATA_TYPE_BFLOAT16, 3, d_in[1], dims, st, box, es, CU_TENSOR_MAP_INTERLEAVE_NONE,
        CU_TENSOR_MAP_SWIZZLE_64B, CU_TENSOR_MAP_L2_PROMOTION_L2_128B, CU_TENSOR_MAP_FLOAT_OOB_FILL_NONE);
  }
  {
    cuuint64_t dims[3] = {64, 512, 8}, st[2] = {1024, 128};
    cuuint32_t box[3] = {64, 64, 2};
    enc(&mo, CU_TENSOR_MAP_DATA_TYPE_BFLOAT16, 3, d_in[3], dims, st, box, es, CU_TENSOR_MAP_INTERLEAVE_NONE,
        CU_TENSOR_MAP_SWIZZLE_128B, CU_TENSOR_MAP_L2_PROMOTION_L2_128B, CU_TENSOR_MAP_FLOAT_OOB_FILL_NONE);
  }
  {
    cuuint64_t dims[4] = {512, 4, 16, 32}, st[3] = {16384, 1024, 65536};
    cuuint32_t box[4] = {64, 4, 16, 2};
    enc(&mu, CU_TENSOR_MAP_DATA_TYPE_BFLOAT16, 4, d_in[4], dims, st, box, es, CU_TENSOR_MAP_INTERLEAVE_NONE,
        CU_TENSOR_MAP_SWIZZLE_128B, CU_TENSOR_MAP_L2_PROMOTION_L2_128B, CU_TENSOR_MAP_FLOAT_OOB_FILL_NONE);
  }
  {
    cuuint64_t dims[2] = {1024, 2048}, st[1] = {2048};
    cuuint32_t box[2] = {64, 16};
    enc(&mout, CU_TENSOR_MAP_DATA_TYPE_BFLOAT16, 2, d_out, dims, st, box, es, CU_TENSOR_MAP_INTERLEAVE_NONE,
        CU_TENSOR_MAP_SWIZZLE_128B, CU_TENSOR_MAP_L2_PROMOTION_NONE, CU_TENSOR_MAP_FLOAT_OOB_FILL_NONE);
  }
  Params P;
  P.x = (const __nv_bfloat16*)d_in[0];
  P.u = (const __nv_bfloat16*)d_in[4];
  P.wphi = (const __nv_bfloat16*)d_in[2];
  P.wo = (const __nv_bfloat16*)d_in[3];
  P.logA = (const __nv_bfloat16*)d_in[5];
  P.Aim = (const __nv_bfloat16*)d_in[6];
  P.Cre = (const __nv_bfloat16*)d_in[7];
  P.Cim = (const __nv_bfloat16*)d_in[8];
  P.logdt = (const __nv_bfloat16*)d_in[9];
  P.Dskip = (const __nv_bfloat16*)d_in[10];
  P.out = (__nv_bfloat16*)d_out;
  cudaGetSymbolAddress((void**)&P.xs, g_x);
  P.ts = nullptr;
  cudaFuncSetAttribute(fused_kernel, cudaFuncAttributeMaxDynamicSharedMemorySize, SMEM_BYTES);
  fused_kernel<<<NCTA, NTHREADS, SMEM_BYTES>>>(P, mx, mw, mo, mu, mout);
}
```

```cpp
#include <cuda_runtime.h>
#include <cuda_bf16.h>
#include <cuda_fp16.h>
#include <cuda.h>
#include <stdint.h>

#define DBG_TS 0

namespace {

constexpr int NTHREADS = 512;
constexpr int NCTA = 128;
constexpr int OFF_W = 0;
constexpr int OFF_X = 98304;
constexpr int OFF_U = OFF_X + 65536;
constexpr int U_CH = 4416, U_ODD = 2240, U_PAD = 128;
constexpr int OFF_STG0 = OFF_U + 18432;
constexpr int SLAB = 3328;
constexpr int OFF_T = OFF_STG0 + 8 * SLAB;
constexpr int T_CH = 5216;
constexpr int T_D = 0;
constexpr int T_5 = 2144;
constexpr int T_3 = T_5 + 384;
constexpr int T_7 = T_5 + 1024;
constexpr int T_9 = T_7 + 320;
constexpr int T_KC = T_9 + 320;
constexpr int T_ST = T_5 - 1024;
constexpr int OFF_PHI = OFF_T + 4 * T_CH;
constexpr int OFF_EYE = OFF_PHI + 1024, OFF_ONE = OFF_EYE + 512;
constexpr int OFF_BAR = OFF_ONE + 256;
constexpr int SMEM_BYTES = OFF_BAR + 512 + 256 * DBG_TS;
constexpr uint32_t SB = 1024;
static_assert(T_KC + 2 * 656 <= T_CH, "table size");
static_assert(SMEM_BYTES <= 232448, "smem");
constexpr int MB_URAW = 0, MB_FULL = 1  , MB_WO = 17, MB_UFULL = 18, MB_O = 19  ,
              MB_EMPTY = 23  , MB_AUX = 39;
__host__ __device__ constexpr uint32_t BAR(int i) { return SB + OFF_BAR + 8 * i; }
constexpr int NB_WG0 = 1, NB_ODONE = 2, NB_ST0 = 3, NB_KV = 5, NB_YZ = 6, NB_INIT = 7, NB_PREP = 8, NB_PROD = 9, NB_KREAD = 10,
              NB_BDONE = 11, NB_GATE = 12  , NB_Y = 7  ;
constexpr int U_AT = 2;
constexpr int ZERO_STEP = 12;
constexpr int SPIN_MAX = 1 << 16;

constexpr int X_CNT = 0;
constexpr int X_PART = 256;
constexpr int X_O = X_PART + 16 * 8 * 144;
constexpr int X_Y = X_O + 32 * 32 * 128;
constexpr int X_UT = X_Y + 512 * 8 * 32;
constexpr int X_SIZE = X_UT + 512 * (U_CH / 16);
__device__ __align__(128) uint4 g_x[X_SIZE];
extern __shared__ uint8_t smem_raw[];
#define TS(i) do {} while (0)
#define TS1(i) do {} while (0)
#define GT(i) do {} while (0)
#define TSDUMP(base) do {} while (0)

__device__ __forceinline__ uint32_t smem_u32(const void* p) { return (uint32_t)__cvta_generic_to_shared(p); }
__device__ __forceinline__ void mbar_arrive(uint32_t b) {
  asm volatile("mbarrier.arrive.shared::cta.b64 _, [%0];" ::"r"(b) : "memory");
}
__device__ __forceinline__ void mbar_wait(uint32_t b) {
  uint32_t done = 0;
#pragma unroll 1
  for (int i = 0; i < SPIN_MAX && !done; i++) {
    asm volatile("{\n.reg .pred p;\nmbarrier.try_wait.parity.shared::cta.b64 p, [%1], 0, 4000;\nselp.u32 %0, 1, 0, p;\n}\n"
                 : "=r"(done) : "r"(b) : "memory");
  }
}
__device__ __forceinline__ void mbar_spin(uint32_t b) {
  uint32_t done = 0;
#pragma unroll 1
  for (int i = 0; i < (SPIN_MAX << 4) && !done; i++) {
    asm volatile("{\n.reg .pred p;\nmbarrier.try_wait.parity.shared::cta.b64 p, [%1], 0;\nselp.u32 %0, 1, 0, p;\n}\n"
                 : "=r"(done) : "r"(b) : "memory");
  }
}
__device__ __forceinline__ void mbar_init(uint32_t b, int n) {
  asm volatile("mbarrier.init.shared::cta.b64 [%0], %1;" ::"r"(b), "r"(n) : "memory");
}
__device__ __forceinline__ void mbar_expect(uint32_t b, int bytes) {
  asm volatile("mbarrier.arrive.expect_tx.shared::cta.b64 _, [%0], %1;" ::"r"(b), "r"(bytes) : "memory");
}
__device__ __forceinline__ void nb_sync(int id, int n) { asm volatile("bar.sync %0, %1;" ::"r"(id), "r"(n) : "memory"); }
__device__ __forceinline__ void nb_arrive(int id, int n) { asm volatile("bar.arrive %0, %1;" ::"r"(id), "r"(n) : "memory"); }
#define ELECT "{\n.reg .pred p;\nelect.sync _|p, 0xffffffff;\n@p "
__device__ __forceinline__ void e_arrive(uint32_t b) {
  asm volatile(ELECT "mbarrier.arrive.shared::cta.b64 _, [%0];\n}\n" ::"r"(b) : "memory");
}
__device__ __forceinline__ void e_expect(uint32_t b, int bytes) {
  asm volatile(ELECT "mbarrier.arrive.expect_tx.shared::cta.b64 _, [%0], %1;\n}\n" ::"r"(b), "r"(bytes) : "memory");
}
__device__ __forceinline__ void e_tma2d(uint32_t dst, const CUtensorMap* m, uint32_t bar, int c0, int c1) {
  asm volatile(ELECT "cp.async.bulk.tensor.2d.shared::cluster.global.mbarrier::complete_tx::bytes [%0], [%1, {%3,%4}], [%2];\n}\n"
               ::"r"(dst), "l"(m), "r"(bar), "r"(c0), "r"(c1) : "memory");
}
__device__ __forceinline__ void e_tma3d(uint32_t dst, const CUtensorMap* m, uint32_t bar, int c0, int c1, int c2) {
  asm volatile(ELECT "cp.async.bulk.tensor.3d.shared::cluster.global.mbarrier::complete_tx::bytes [%0], [%1, {%3,%4,%5}], [%2];\n}\n"
               ::"r"(dst), "l"(m), "r"(bar), "r"(c0), "r"(c1), "r"(c2) : "memory");
}
__device__ __forceinline__ void e_tma4d(uint32_t dst, const CUtensorMap* m, uint32_t bar, int c0, int c3) {
  asm volatile(ELECT "cp.async.bulk.tensor.4d.shared::cluster.global.mbarrier::complete_tx::bytes [%0], [%1, {%3,%5,%5,%4}], [%2];\n}\n"
               ::"r"(dst), "l"(m), "r"(bar), "r"(c0), "r"(c3), "r"(0) : "memory");
}
__device__ __forceinline__ void e_bulk(uint32_t dst, const void* src, int bytes, uint32_t bar) {
  asm volatile(ELECT "cp.async.bulk.shared::cluster.global.mbarrier::complete_tx::bytes [%0], [%1], %2, [%3];\n}\n"
               ::"r"(dst), "l"(src), "r"(bytes), "r"(bar) : "memory");
}
__device__ __forceinline__ void e_prefetch(const void* p, int bytes) {
  asm volatile(ELECT "cp.async.bulk.prefetch.L2.global [%0], %1;\n}\n" ::"l"(p), "r"(bytes) : "memory");
}
__device__ __forceinline__ void e_store2d(const CUtensorMap* m, uint32_t src, int c0, int c1) {
  asm volatile(ELECT "cp.async.bulk.tensor.2d.global.shared::cta.bulk_group [%0, {%2,%3}], [%1];\n}\n"
               ::"l"(m), "r"(src), "r"(c0), "r"(c1) : "memory");
}
__host__ __device__ constexpr uint64_t mkdesc(uint32_t addr, uint32_t lbo, uint32_t sbo, int swz) {
  return (uint64_t)((addr & 0x3FFFF) >> 4) | ((uint64_t)(lbo >> 4) << 16) | ((uint64_t)(sbo >> 4) << 32) |
         ((uint64_t)swz << 62);
}
#define SPLIT() asm volatile("{\n.reg .pred p;\nsetp.eq.u32 p, %0, %1;\n@p exit;\n}\n" ::"r"(blockIdx.y), "n"(__LINE__) : "memory")
#define SPLITN(n) asm volatile("{\n.reg .pred p;\nsetp.eq.u32 p, %0, %1;\n@p exit;\n}\n" ::"r"(blockIdx.y), "r"(4096 + (n)) : "memory")
#define WG_FENCE() asm volatile("wgmma.fence.sync.aligned;" ::: "memory")
#define WG_COMMIT() asm volatile("wgmma.commit_group.sync.aligned;" ::: "memory")
#define WG_WAIT(n) asm volatile("wgmma.wait_group.sync.aligned " #n ";" ::: "memory")

__device__ __forceinline__ void mma(float& d0, float& d1, float& d2, float& d3, uint32_t a0, uint32_t a1, uint32_t a2,
                                    uint32_t a3, uint32_t b0, uint32_t b1) {
  asm volatile("mma.sync.aligned.m16n8k16.row.col.f32.bf16.bf16.f32 {%0,%1,%2,%3},{%4,%5,%6,%7},{%8,%9},{%0,%1,%2,%3};"
               : "+f"(d0), "+f"(d1), "+f"(d2), "+f"(d3)
               : "r"(a0), "r"(a1), "r"(a2), "r"(a3), "r"(b0), "r"(b1));
}
__device__ __forceinline__ void mmac(float (&d)[4], uint32_t a0, uint32_t a1, uint32_t a2, uint32_t a3, uint32_t b0,
                                     uint32_t b1, const float (&c)[4]) {
  asm volatile("mma.sync.aligned.m16n8k16.row.col.f32.bf16.bf16.f32 {%0,%1,%2,%3},{%4,%5,%6,%7},{%8,%9},{%10,%11,%12,%13};"
               : "=f"(d[0]), "=f"(d[1]), "=f"(d[2]), "=f"(d[3])
               : "r"(a0), "r"(a1), "r"(a2), "r"(a3), "r"(b0), "r"(b1), "f"(c[0]), "f"(c[1]), "f"(c[2]), "f"(c[3]));
}
__device__ __forceinline__ void mma_h(float (&d)[4], const uint32_t (&a)[4], uint32_t b0, uint32_t b1) {
  asm volatile("mma.sync.aligned.m16n8k16.row.col.f32.f16.f16.f32 {%0,%1,%2,%3},{%4,%5,%6,%7},{%8,%9},{%0,%1,%2,%3};"
               : "+f"(d[0]), "+f"(d[1]), "+f"(d[2]), "+f"(d[3]) : "r"(a[0]), "r"(a[1]), "r"(a[2]), "r"(a[3]), "r"(b0), "r"(b1));
}
__device__ __forceinline__ void mma0(float& d0, float& d1, float& d2, float& d3, uint32_t a0, uint32_t a1, uint32_t a2,
                                     uint32_t a3, uint32_t b0, uint32_t b1) {
  asm volatile("mma.sync.aligned.m16n8k16.row.col.f32.bf16.bf16.f32 {%0,%1,%2,%3},{%4,%5,%6,%7},{%8,%9},{%10,%10,%10,%10};"
               : "=f"(d0), "=f"(d1), "=f"(d2), "=f"(d3)
               : "r"(a0), "r"(a1), "r"(a2), "r"(a3), "r"(b0), "r"(b1), "f"(0.f));
}
__device__ __forceinline__ uint32_t pack_bf(float lo, float hi) {
  uint32_t r;
  asm("cvt.rn.bf16x2.f32 %0, %1, %2;" : "=r"(r) : "f"(hi), "f"(lo));
  return r;
}
__device__ __forceinline__ float bf_lo(uint32_t w) { return __uint_as_float(w << 16); }
__device__ __forceinline__ float bf_hi(uint32_t w) { return __uint_as_float(w & 0xffff0000u); }
__device__ __forceinline__ float bf_round(float x) { return __bfloat162float(__float2bfloat16_rn(x)); }
__device__ __forceinline__ uint32_t bmax2(uint32_t a, uint32_t b) {
  uint32_t r; asm("max.bf16x2 %0, %1, %2;" : "=r"(r) : "r"(a), "r"(b)); return r;
}
__device__ __forceinline__ uint32_t bmin2(uint32_t a, uint32_t b) {
  uint32_t r; asm("min.bf16x2 %0, %1, %2;" : "=r"(r) : "r"(a), "r"(b)); return r;
}
__device__ __forceinline__ float ex2(float x) { float r; asm("ex2.approx.ftz.f32 %0, %1;" : "=f"(r) : "f"(x)); return r; }
__device__ __forceinline__ float rcp(float x) { float r; asm("rcp.approx.ftz.f32 %0, %1;" : "=f"(r) : "f"(x)); return r; }
__device__ __forceinline__ void ldsm4(uint32_t (&r)[4], uint32_t a) {
  asm volatile("ldmatrix.sync.aligned.m8n8.x4.shared.b16 {%0,%1,%2,%3}, [%4];"
               : "=r"(r[0]), "=r"(r[1]), "=r"(r[2]), "=r"(r[3]) : "r"(a) : "memory");
}
__device__ __forceinline__ void ldsm4t(uint32_t (&r)[4], uint32_t a) {
  asm volatile("ldmatrix.sync.aligned.m8n8.x4.trans.shared.b16 {%0,%1,%2,%3}, [%4];"
               : "=r"(r[0]), "=r"(r[1]), "=r"(r[2]), "=r"(r[3]) : "r"(a) : "memory");
}
__device__ __forceinline__ void stsm4(uint32_t a, uint32_t r0, uint32_t r1, uint32_t r2, uint32_t r3) {
  asm volatile("stmatrix.sync.aligned.m8n8.x4.shared.b16 [%0], {%1,%2,%3,%4};"
               ::"r"(a), "r"(r0), "r"(r1), "r"(r2), "r"(r3) : "memory");
}
__device__ __forceinline__ uint32_t lds32(uint32_t a) {
  uint32_t r; asm volatile("ld.shared.u32 %0, [%1];" : "=r"(r) : "r"(a) : "memory"); return r;
}
__device__ __forceinline__ uint32_t lds16(uint32_t a) {
  uint32_t r; asm volatile("{\n.reg .u16 h;\nld.shared.u16 h, [%1];\ncvt.u32.u16 %0, h;\n}\n" : "=r"(r) : "r"(a) : "memory"); return r;
}
__device__ __forceinline__ uint2 lds64(uint32_t a) {
  uint2 r; asm volatile("ld.shared.v2.u32 {%0,%1}, [%2];" : "=r"(r.x), "=r"(r.y) : "r"(a) : "memory"); return r;
}
__device__ __forceinline__ uint4 lds128(uint32_t a) {
  uint4 r;
  asm volatile("ld.shared.v4.u32 {%0,%1,%2,%3}, [%4];" : "=r"(r.x), "=r"(r.y), "=r"(r.z), "=r"(r.w) : "r"(a) : "memory");
  return r;
}
__device__ __forceinline__ void sts32(uint32_t a, uint32_t v) { asm volatile("st.shared.u32 [%0], %1;" ::"r"(a), "r"(v) : "memory"); }
__device__ __forceinline__ void sts16(uint32_t a, uint32_t v) {
  asm volatile("{\n.reg .u16 h;\ncvt.u16.u32 h, %1;\nst.shared.u16 [%0], h;\n}\n" ::"r"(a), "r"(v) : "memory");
}
__device__ __forceinline__ void sts64(uint32_t a, uint32_t x, uint32_t y) {
  asm volatile("st.shared.v2.u32 [%0], {%1,%2};" ::"r"(a), "r"(x), "r"(y) : "memory");
}
__device__ __forceinline__ void sts128(uint32_t a, uint32_t x, uint32_t y, uint32_t z, uint32_t w) {
  asm volatile("st.shared.v4.u32 [%0], {%1,%2,%3,%4};" ::"r"(a), "r"(x), "r"(y), "r"(z), "r"(w) : "memory");
}
__device__ __forceinline__ uint4 ld_x(const uint4* p) {
  uint4 r;
  asm volatile("{\n.reg .b128 t;\nld.relaxed.gpu.global.b128 t, [%4];\nmov.b128 {%0,%1,%2,%3}, t;\n}\n"
               : "=r"(r.x), "=r"(r.y), "=r"(r.z), "=r"(r.w) : "l"(p) : "memory");
  return r;
}
__device__ __forceinline__ uint32_t ld_x32(const uint32_t* p) {
  uint32_t r; asm volatile("ld.relaxed.gpu.global.u32 %0, [%1];" : "=r"(r) : "l"(p) : "memory"); return r;
}
__device__ __forceinline__ void st_x(uint4* p, uint32_t x, uint32_t y, uint32_t z, uint32_t w) {
  asm volatile("{\n.reg .b128 t;\nmov.b128 t, {%1,%2,%3,%4};\nst.relaxed.gpu.global.b128 [%0], t;\n}\n"
               ::"l"(p), "r"(x), "r"(y), "r"(z), "r"(w) : "memory");
}
__device__ __forceinline__ void st_x32(uint32_t* p, uint32_t x) {
  asm volatile("st.relaxed.gpu.global.u32 [%0], %1;" ::"l"(p), "r"(x) : "memory");
}
__device__ __forceinline__ uint32_t nz(uint32_t w) { return max(w, 1u); }
__device__ __forceinline__ uint32_t fu(float x) { return __float_as_uint(x); }
__device__ __forceinline__ float uf(uint32_t x) { return __uint_as_float(x); }

__device__ __forceinline__ void wgmma_ss_n96(float (&d)[48], uint64_t da, uint64_t db, int sc) {
  asm volatile("{\n.reg .pred p;\nsetp.ne.b32 p, %50, 0;\n"
      "wgmma.mma_async.sync.aligned.m64n96k16.f32.bf16.bf16 "
      "{%0,%1,%2,%3,%4,%5,%6,%7,%8,%9,%10,%11,%12,%13,%14,%15,%16,%17,%18,%19,%20,%21,%22,%23,%24,%25,%26,%27,%28,%29,%30,%31,%32,%33,%34,%35,%36,%37,%38,%39,%40,%41,%42,%43,%44,%45,%46,%47}, "
      "%48, %49, p, 1, 1, 0, 1;\n}\n"
      : "+f"(d[0]), "+f"(d[1]), "+f"(d[2]), "+f"(d[3]), "+f"(d[4]), "+f"(d[5]), "+f"(d[6]), "+f"(d[7]),
        "+f"(d[8]), "+f"(d[9]), "+f"(d[10]), "+f"(d[11]), "+f"(d[12]), "+f"(d[13]), "+f"(d[14]), "+f"(d[15]),
        "+f"(d[16]), "+f"(d[17]), "+f"(d[18]), "+f"(d[19]), "+f"(d[20]), "+f"(d[21]), "+f"(d[22]), "+f"(d[23]),
        "+f"(d[24]), "+f"(d[25]), "+f"(d[26]), "+f"(d[27]), "+f"(d[28]), "+f"(d[29]), "+f"(d[30]), "+f"(d[31]),
        "+f"(d[32]), "+f"(d[33]), "+f"(d[34]), "+f"(d[35]), "+f"(d[36]), "+f"(d[37]), "+f"(d[38]), "+f"(d[39]),
        "+f"(d[40]), "+f"(d[41]), "+f"(d[42]), "+f"(d[43]), "+f"(d[44]), "+f"(d[45]), "+f"(d[46]), "+f"(d[47])
      : "l"(da), "l"(db), "r"(sc));
}

__device__ __forceinline__ void wgmma_ss_n128(float (&d)[64], uint64_t da, uint64_t db, int sc) {
  asm volatile("{\n.reg .pred p;\nsetp.ne.b32 p, %66, 0;\n"
      "wgmma.mma_async.sync.aligned.m64n128k16.f32.bf16.bf16 "
      "{%0,%1,%2,%3,%4,%5,%6,%7,%8,%9,%10,%11,%12,%13,%14,%15,%16,%17,%18,%19,%20,%21,%22,%23,%24,%25,%26,%27,%28,%29,%30,%31,%32,%33,%34,%35,%36,%37,%38,%39,%40,%41,%42,%43,%44,%45,%46,%47,%48,%49,%50,%51,%52,%53,%54,%55,%56,%57,%58,%59,%60,%61,%62,%63}, "
      "%64, %65, p, 1, 1, 0, 1;\n}\n"
      : "+f"(d[0]), "+f"(d[1]), "+f"(d[2]), "+f"(d[3]), "+f"(d[4]), "+f"(d[5]), "+f"(d[6]), "+f"(d[7]),
        "+f"(d[8]), "+f"(d[9]), "+f"(d[10]), "+f"(d[11]), "+f"(d[12]), "+f"(d[13]), "+f"(d[14]), "+f"(d[15]),
        "+f"(d[16]), "+f"(d[17]), "+f"(d[18]), "+f"(d[19]), "+f"(d[20]), "+f"(d[21]), "+f"(d[22]), "+f"(d[23]),
        "+f"(d[24]), "+f"(d[25]), "+f"(d[26]), "+f"(d[27]), "+f"(d[28]), "+f"(d[29]), "+f"(d[30]), "+f"(d[31]),
        "+f"(d[32]), "+f"(d[33]), "+f"(d[34]), "+f"(d[35]), "+f"(d[36]), "+f"(d[37]), "+f"(d[38]), "+f"(d[39]),
        "+f"(d[40]), "+f"(d[41]), "+f"(d[42]), "+f"(d[43]), "+f"(d[44]), "+f"(d[45]), "+f"(d[46]), "+f"(d[47]),
        "+f"(d[48]), "+f"(d[49]), "+f"(d[50]), "+f"(d[51]), "+f"(d[52]), "+f"(d[53]), "+f"(d[54]), "+f"(d[55]),
        "+f"(d[56]), "+f"(d[57]), "+f"(d[58]), "+f"(d[59]), "+f"(d[60]), "+f"(d[61]), "+f"(d[62]), "+f"(d[63])
      : "l"(da), "l"(db), "r"(sc));
}

__device__ __forceinline__ void wgmma_ss_n40(float (&d)[20], uint64_t da, uint64_t db, int sc) {
  asm volatile("{\n.reg .pred p;\nsetp.ne.b32 p, %22, 0;\n"
      "wgmma.mma_async.sync.aligned.m64n40k16.f32.bf16.bf16 "
      "{%0,%1,%2,%3,%4,%5,%6,%7,%8,%9,%10,%11,%12,%13,%14,%15,%16,%17,%18,%19}, "
      "%20, %21, p, 1, 1, 1, 1;\n}\n"
      : "+f"(d[0]), "+f"(d[1]), "+f"(d[2]), "+f"(d[3]), "+f"(d[4]), "+f"(d[5]), "+f"(d[6]), "+f"(d[7]),
        "+f"(d[8]), "+f"(d[9]), "+f"(d[10]), "+f"(d[11]), "+f"(d[12]), "+f"(d[13]), "+f"(d[14]), "+f"(d[15]),
        "+f"(d[16]), "+f"(d[17]), "+f"(d[18]), "+f"(d[19])
      : "l"(da), "l"(db), "r"(sc));
}

__device__ __forceinline__ void wgmma_rs_n8(float (&d)[4], const uint4& a, uint64_t db, int sc) {
  asm volatile("{\n.reg .pred p;\nsetp.ne.b32 p, %9, 0;\n"
      "wgmma.mma_async.sync.aligned.m64n8k16.f32.bf16.bf16 "
      "{%0,%1,%2,%3}, "
      "{%4,%5,%6,%7}, %8, p, 1, 1, 1;\n}\n"
      : "+f"(d[0]), "+f"(d[1]), "+f"(d[2]), "+f"(d[3])
      : "r"(a.x), "r"(a.y), "r"(a.z), "r"(a.w), "l"(db), "r"(sc));
}

__device__ __forceinline__ void wgmma_rs_n16(float (&d)[8], const uint4& a, uint64_t db, int sc) {
  asm volatile("{\n.reg .pred p;\nsetp.ne.b32 p, %13, 0;\n"
      "wgmma.mma_async.sync.aligned.m64n16k16.f32.bf16.bf16 "
      "{%0,%1,%2,%3,%4,%5,%6,%7}, "
      "{%8,%9,%10,%11}, %12, p, 1, 1, 1;\n}\n"
      : "+f"(d[0]), "+f"(d[1]), "+f"(d[2]), "+f"(d[3]), "+f"(d[4]), "+f"(d[5]), "+f"(d[6]), "+f"(d[7])
      : "r"(a.x), "r"(a.y), "r"(a.z), "r"(a.w), "l"(db), "r"(sc));
}

__device__ __forceinline__ void wgmma_rs_n24(float (&d)[12], const uint4& a, uint64_t db, int sc) {
  asm volatile("{\n.reg .pred p;\nsetp.ne.b32 p, %17, 0;\n"
      "wgmma.mma_async.sync.aligned.m64n24k16.f32.bf16.bf16 "
      "{%0,%1,%2,%3,%4,%5,%6,%7,%8,%9,%10,%11}, "
      "{%12,%13,%14,%15}, %16, p, 1, 1, 1;\n}\n"
      : "+f"(d[0]), "+f"(d[1]), "+f"(d[2]), "+f"(d[3]), "+f"(d[4]), "+f"(d[5]), "+f"(d[6]), "+f"(d[7]),
        "+f"(d[8]), "+f"(d[9]), "+f"(d[10]), "+f"(d[11])
      : "r"(a.x), "r"(a.y), "r"(a.z), "r"(a.w), "l"(db), "r"(sc));
}

struct Params {
  const __nv_bfloat16 *logA, *Aim, *Cre, *Cim, *logdt, *Dskip, *x, *wphi, *wo;
  __nv_bfloat16* out;
  uint4* xs;
  long long* ts;
};

__device__ __forceinline__ uint4 tr_row(const uint4 (&v)[8], int i) {
  uint32_t o[4];
#pragma unroll
  for (int m = 0; m < 4; m++) {
    const uint4 &ra = v[2 * m], &rb = v[2 * m + 1];
    const int k = i >> 1;
    const uint32_t xa = k == 0 ? ra.x : k == 1 ? ra.y : k == 2 ? ra.z : ra.w;
    const uint32_t xb = k == 0 ? rb.x : k == 1 ? rb.y : k == 2 ? rb.z : rb.w;
    o[m] = __byte_perm(xa, xb, (i & 1) ? 0x7632 : 0x5410);
  }
  return make_uint4(o[0], o[1], o[2], o[3]);
}

struct cpx { float r, i; };
__device__ __forceinline__ cpx csq(cpx a) { return {a.r * a.r - a.i * a.i, 2.f * (a.r * a.i)}; }
__device__ __forceinline__ cpx polar(float e, float t) {
  const float m = ex2(e);
  return {m * __cosf(t), m * __sinf(t)};
}

struct KgenRaw { uint32_t la, ai, cr, ci, ldt; };
__device__ __forceinline__ KgenRaw kgen_load(const Params& P, int d, int unit, int lane, int on) {
  const int o = d * 64 + unit * 32 + lane;
  KgenRaw r = {0, 0, 0, 0, 0};
  asm volatile("{\n.reg .pred p;\nsetp.ne.b32 p, %10, 0;\n@p ld.global.nc.u32 %0, [%5];\n@p ld.global.nc.u32 %1, [%6];\n"
               "@p ld.global.nc.u32 %2, [%7];\n@p ld.global.nc.u32 %3, [%8];\n@p ld.global.nc.u16 %4, [%9];\n}\n"
               : "+r"(r.la), "+r"(r.ai), "+r"(r.cr), "+r"(r.ci), "+r"(r.ldt)
               : "l"((const uint32_t*)P.logA + o), "l"((const uint32_t*)P.Aim + o), "l"((const uint32_t*)P.Cre + o),
                 "l"((const uint32_t*)P.Cim + o), "l"(P.logdt + d), "r"(on));
  return r;
}
struct hc { __half2 r, i; };
struct cpx2 { cpx a, b; };
__device__ __forceinline__ cpx2 csq2(const cpx2& v) { return {csq(v.a), csq(v.b)}; }
__device__ __forceinline__ hc toh(const cpx2& v) { return {__floats2half2_rn(v.a.r, v.b.r), __floats2half2_rn(v.a.i, v.b.i)}; }
__device__ __forceinline__ hc hmul(const hc& z, const hc& w) {
  return {__hfma2(z.r, w.r, __hneg2(__hmul2(z.i, w.i))), __hfma2(z.r, w.i, __hmul2(z.i, w.r))};
}
__device__ __forceinline__ hc hmulc(const hc& z, const hc& w) {
  return {__hfma2(z.r, w.r, __hmul2(z.i, w.i)), __hfma2(z.i, w.r, __hneg2(__hmul2(z.r, w.i)))};
}
__device__ __forceinline__ uint32_t hu(__half2 v) { return *(const uint32_t*)&v; }
__device__ __forceinline__ __half2 uh(uint32_t v) { return *(const __half2*)&v; }

struct KgenAddr { uint32_t sa, lb, lm[4]; };
__device__ __forceinline__ KgenAddr kgen_addr(int lane, uint32_t buf) {
  KgenAddr a;
  a.sa = buf + (lane & 7) * 128 + ((((lane >> 3) ^ lane) & 7) << 4);
  const int q = lane >> 4;
  const uint32_t b = buf + ((lane >> 3) & 1) * 1024 + q * 128;
  a.lb = b + (((lane ^ q) & 7) << 4);
  a.lm[0] = b + (q << 4);
  a.lm[1] = b + ((1 ^ q) << 4);
  a.lm[2] = b + (((2 + (lane & 1)) ^ q) << 4);
  a.lm[3] = b + (((4 + (lane & 3)) ^ q) << 4);
  asm volatile("" : "+r"(a.sa), "+r"(a.lb), "+r"(a.lm[0]), "+r"(a.lm[1]), "+r"(a.lm[2]), "+r"(a.lm[3]));
  return a;
}
__device__ __forceinline__ void kgen_unit(const KgenRaw& r, const KgenAddr& ad, uint32_t zero, float (&k)[5][4], float& k2048, float& sc) {
  const float dt = bf_round(expf(bf_lo(r.ldt)));
  const uint32_t ar = pack_bf(ex2(bf_lo(r.la) * 1.4426950408889634f), ex2(bf_hi(r.la) * 1.4426950408889634f));
  const float ca = dt * -1.4426950408889634f, a0 = bf_lo(ar) * ca, a1 = bf_hi(ar) * ca;
  const float f0 = bf_lo(r.ai) * dt, f1 = bf_hi(r.ai) * dt;
  const float r0 = f0 * 20.21267777267071f, r1 = f1 * 20.21267777267071f;
  const uint32_t cm = __vmaxu2(r.cr & 0x7fff7fffu, r.ci & 0x7fff7fffu);
  const uint32_t ex = min(max(__reduce_max_sync(0xffffffffu, max(cm >> 16, cm & 0xffffu)) >> 7, 1u), 253u);
  const float cs = uf((254u - ex) << 23);
  sc = 2.f * dt * uf(ex << 23);
  const cpx2 C = {{bf_lo(r.cr) * cs, bf_lo(r.ci) * -cs}, {bf_hi(r.cr) * cs, bf_hi(r.ci) * -cs}};
  auto put = [&](const hc (&v)[8]) {
    stsm4(ad.sa, hu(v[0].r), hu(v[1].r), hu(v[2].r), hu(v[3].r));
    stsm4(ad.sa + 1024, hu(v[0].i), hu(v[1].i), hu(v[2].i), hu(v[3].i));
    stsm4(ad.sa ^ 64, hu(v[4].r), hu(v[5].r), hu(v[6].r), hu(v[7].r));
    stsm4((ad.sa ^ 64) + 1024, hu(v[4].i), hu(v[5].i), hu(v[6].i), hu(v[7].i));
    __syncwarp();
  };
  auto get = [&](uint32_t (&o)[4][4], uint32_t a) {
#pragma unroll
    for (int i = 0; i < 4; i++) ldsm4(o[i], (a ^ (i << 5)) + i * 256);
  };
  auto at = [](const uint32_t (&o)[4][4], int s) { return hc{uh(o[s >> 1][2 * (s & 1)]), uh(o[s >> 1][2 * (s & 1) + 1])}; };
  uint32_t A[8][4];
  auto tile = [&](int j, const uint32_t (&B)[4][4]) {
    k[j][0] = k[j][1] = k[j][2] = k[j][3] = 0.f;
#pragma unroll
    for (int s = 0; s < 8; s++) mma_h(k[j], A[s], B[s >> 1][2 * (s & 1)], B[s >> 1][2 * (s & 1) + 1]);
  };
  const cpx2 w1 = {polar(a0, f0), polar(a1, f1)};
  const cpx2 w127 = {polar(a0 * 127.f, (r0 - rintf(r0)) * 6.283185307179586f), polar(a1 * 127.f, (r1 - rintf(r1)) * 6.283185307179586f)};
  const cpx2 w2 = csq2(w1), w4 = csq2(w2);
  uint32_t T0[4][4], X[4][4], M[3][4][4];
  {
    hc t[8];
    t[0] = {uh(0x3C003C00u), uh(0u)}; t[1] = toh(w1); t[2] = toh(w2); t[4] = toh(w4);
    t[3] = hmul(t[1], t[2]); t[5] = hmul(t[1], t[4]); t[6] = hmul(t[2], t[4]); t[7] = hmul(t[3], t[4]);
    put(t); get(T0, ad.lb);
  }
  const cpx2 w8 = csq2(w4), w16 = csq2(w8), w32 = csq2(w16), w64 = csq2(w32);
  {
    const hc m8 = toh(w8), m16 = toh(w16), m32 = toh(w32);
    hc a[8];
    a[0] = toh(C); a[1] = hmulc(a[0], m8);
    a[2] = hmulc(a[0], m16); a[3] = hmulc(a[1], m16);
#pragma unroll
    for (int i = 0; i < 4; i++) a[4 + i] = hmulc(a[i], m32);
    put(a); get(X, ad.lb);
  }
    const cpx2 w128 = {{w127.a.r * w1.a.r - w127.a.i * w1.a.i, w127.a.r * w1.a.i + w127.a.i * w1.a.r},
                     {w127.b.r * w1.b.r - w127.b.i * w1.b.i, w127.b.r * w1.b.i + w127.b.i * w1.b.r}};
  const cpx2 w256 = csq2(w128), w512 = csq2(w256);
  const hc m128 = toh(w128), m256 = toh(w256), m512 = toh(w512);
  {
    const hc m254 = toh(csq2(w127)), m127 = toh(w127);
    hc m[8];
    m[0] = toh(w64); m[1] = m128; m[2] = m256; m[3] = hmul(m127, m256);
    m[4] = m512; m[5] = hmul(m127, m512); m[6] = hmul(m[4], m254); m[7] = hmul(m[5], m254);
    put(m);
    get(M[0], ad.lm[0]);
#pragma unroll
    for (int s = 0; s < 8; s++) {
      const hc z = at(X, s), y = hmulc(z, at(M[0], s));
      A[s][0] = hu(z.r) + zero; A[s][1] = hu(y.r); A[s][2] = hu(z.i) + zero; A[s][3] = hu(y.i);
    }
#pragma unroll
    for (int i = 0; i < 3; i++) get(M[i], ad.lm[i + 1]);
  }
  tile(0, T0);
  const cpx2 w1024 = csq2(w512), we = csq2(w1024);
  {
    hc t[8];
    t[0] = toh(w1024); t[1] = hmul(t[0], m128);
    t[2] = hmul(t[0], m256); t[3] = hmul(t[1], m256);
#pragma unroll
    for (int i = 0; i < 4; i++) t[4 + i] = hmul(t[i], m512);
    put(t); get(X, ad.lb);
  }
  k2048 = (C.a.r * we.a.r + C.a.i * we.a.i + C.b.r * we.b.r + C.b.i * we.b.i) * sc;
#pragma unroll
  for (int j = 1; j < 5; j++) k[j][0] = k[j][1] = k[j][2] = k[j][3] = 0.f;
#pragma unroll
  for (int s = 0; s < 8; s++) {
#pragma unroll
    for (int j = 0; j < 3; j++) {
      const hc y = hmul(at(T0, s), at(M[j], s));
      mma_h(k[1 + j], A[s], hu(y.r), hu(y.i));
    }
    mma_h(k[4], A[s], X[s >> 1][2 * (s & 1)], X[s >> 1][2 * (s & 1) + 1]);
  }
}

__device__ __forceinline__ void build_tables(uint32_t tb, int lane, float (&k)[5][4], float k2048) {
  const int g = lane >> 2, c = lane & 3;
  const uint32_t kc = tb + T_KC + 16;
  {
    const uint32_t a0 = kc + 16 * g + 4 * c, a2 = kc + 2 * (256 + 4 * g + c);
    const uint32_t a3 = kc + 2 * (384 + 2 * g + 64 * (c & 1) + (c >> 1)), a4 = kc + 2 * (512 + g + 32 * c);
#pragma unroll
    for (int r = 0; r < 2; r++) {
      sts32(a0 + 128 * r, pack_bf(k[0][2 * r], k[0][2 * r + 1]));
      sts32(a0 + 128 * r + 256, pack_bf(k[1][2 * r], k[1][2 * r + 1]));
      const uint32_t w2 = pack_bf(k[2][2 * r], k[2][2 * r + 1]);
      const uint32_t w3 = pack_bf(k[3][2 * r], k[3][2 * r + 1]);
      const uint32_t w4 = pack_bf(k[4][2 * r], k[4][2 * r + 1]);
      sts16(a2 + 64 * r, w2); sts16(a2 + 64 * r + 128, w2 >> 16);
      sts16(a3 + 32 * r, w3); sts16(a3 + 32 * r + 64, w3 >> 16);
      sts16(a4 + 16 * r, w4); sts16(a4 + 16 * r + 32, w4 >> 16);
    }
  }
  if (lane == 0) { sts16(kc + 2 * 640, pack_bf(k2048, 0.f)); sts32(kc - 4, 0); }
  __syncwarp();
  const uint32_t td = tb + T_D + 32;
#pragma unroll
  for (int hf = 0; hf < 2; hf++) {
    const uint2 v = lds64(kc + 256 * hf + 8 * lane);
    const uint32_t pv = lds32(kc + 256 * hf + 8 * lane - 4);
    sts128(td + 512 * hf + 16 * lane, __byte_perm(v.x, pv, 0x7610), __byte_perm(v.x, v.x, 0x1032), __byte_perm(v.y, v.x, 0x7610),
           __byte_perm(v.y, v.y, 0x1032));
  }
#pragma unroll
  for (int hf = 0; hf < 2; hf++) {
    const uint32_t v = lds32(kc + 512 + 128 * hf + 4 * lane), nx = lds32(kc + 516 + 128 * hf + 4 * lane);
    uint32_t w0 = __byte_perm(v, v, 0x1010);
    const uint32_t w1 = w0;
    if (hf == 0) { const uint32_t pv = lds32(kc + 508); if (lane == 0) w0 = __byte_perm(v, pv, 0x7610); }
    sts128(td + 1024 + 512 * hf + 16 * lane, w0, w1, __byte_perm(v, v, 0x1032), __byte_perm(nx, v, 0x7610));
  }
  {
    const uint32_t kk = lds16(kc + 2 * 384);
    const uint32_t w = lane < 3 ? (kk | (kk << 16)) : (lane == 3 ? (kk << 16) : 0u);
    if (lane < 24) sts32(td + 4 * (lane < 16 ? 512 + lane : lane - 24), w);
    const uint32_t lo_ = lds16(kc + 2 * 511), le_ = lds16(kc + 2 * 512);
    const uint32_t ja = tb + T_5 + (lane < 16 ? 4 * lane : 256 + 4 * lane);
    sts32(ja, lane == 16 ? (le_ << 16) : 0u);
    sts32(ja + 384, lane == 16 ? (lo_ << 16) : 0u);
    sts32(tb + (lane < 16 ? T_7 : T_9 - 64) + 4 * lane, 0u);
  }
#pragma unroll
  for (int s = 0; s < 2; s++) {
    const uint32_t b = kc + 2 * (s ? 512 : 384) + 8 * lane;
    const uint2 v = lds64(b);
    uint32_t em = lds16(b - 2), e0 = v.x;
    const uint32_t e4 = lds16(b + 8);
    if (lane == 0) { em = 0; e0 = 0; }
    sts64(tb + (s ? T_7 : T_3) + 64 + 8 * lane, __byte_perm(v.x, em, 0x5432), __byte_perm(v.y, v.x, 0x7632));
    sts64(tb + (s ? T_9 : T_5) + 64 + 8 * lane, __byte_perm(v.y, e0, 0x5410), __byte_perm(e4, v.y, 0x5410));
  }
  __syncwarp();
}

__device__ __forceinline__ uint32_t box2w(int lo, int n, int o) {
  return ((unsigned)(o - lo) < (unsigned)n ? 0x3F80u : 0u) | ((unsigned)(o + 1 - lo) < (unsigned)n ? 0x3F800000u : 0u);
}

__device__ __forceinline__ void conv_channel(uint32_t ub, uint32_t tb, int lane, uint4* ydst) {
  const int g = lane >> 2, c = lane & 3, x = g - 2 * c;
  const int mi = lane >> 3;
  const uint32_t qa = ub + U_PAD + 16 * (lane & 7) + ((mi == 0 || mi == 3) ? U_ODD : 0) - (mi == 0 ? 16 : 0);
  const uint32_t hb = ub + U_PAD + (mi & 1) * U_ODD + 16 * ((lane >> 4) + (lane & 7)) - 16;
  const uint32_t kv = lds16(tb + T_KC + 16 + 2 * 512);
  const int oh = c < 2 ? 8 + 2 * c : 2 * c - 8, og = c < 3 ? 2 * c : -10;
  uint32_t bx[4] = {box2w(g - 4, 9, 2 * c), box2w(g - 3, 7, 2 * c), box2w(g - 4, 9, oh), box2w(g - 3, 7, oh)};
  uint32_t by[4] = {box2w(g - 10, 5, 2 * c - 8), box2w(g - 5, 3, 2 * c - 8), box2w(g - 10, 5, og), box2w(g - 5, 3, og)};
  uint32_t lb0 = ((unsigned)(x + 5) < 2u ? kv : 0u) | ((unsigned)(x + 4) < 2u ? kv << 16 : 0u);
  uint32_t lb1 = ((unsigned)(x - 3) < 2u ? kv : 0u) | ((unsigned)(x - 4) < 2u ? kv << 16 : 0u);
  const int q0 = g - 1, q1 = c < 3 ? g : g - 2;
  uint32_t y0a = ub + U_PAD + (q0 & 1) * U_ODD + 16 * (q0 >> 1) + 4 * c;
  uint32_t y1a = ub + U_PAD + (q1 & 1) * U_ODD + 16 * (q1 >> 1) + 4 * c;
#pragma unroll
  for (int i = 0; i < 4; i++) asm volatile("" : "+r"(bx[i]), "+r"(by[i]));
  asm volatile("" : "+r"(lb0), "+r"(lb1), "+r"(y0a), "+r"(y1a));
  mbar_wait(BAR(MB_UFULL));
  mbar_spin(BAR(MB_EMPTY + 15));
  TS(36);
  float acc[16][4];
  {
    uint32_t z09[8], z07[8], zm9[8], zm7[8];
#pragma unroll
    for (int i = 0; i < 8; i++) {
      uint32_t h[4];
      ldsm4(h, hb + 128 * i);
      float y0, y1, y2, y3, w0, w1, w2, w3;
      mma0(y0, y1, y2, y3, bx[0], bx[1], bx[2], bx[3], h[2], c < 2 ? h[3] : h[1]);
      mma0(w0, w1, w2, w3, bx[0], bx[1], bx[2], bx[3], h[1], c < 2 ? h[2] : h[0]);
      z09[i] = pack_bf(y0, y1); z07[i] = pack_bf(y2, y3);
      zm9[i] = pack_bf(w0, w1); zm7[i] = pack_bf(w2, w3);
    }
  uint32_t f3[3][4][4];
  {
    const uint32_t fa = tb + T_7 + 4 * (16 + x);
#pragma unroll
    for (int tt = 0; tt < 3; tt++)
#pragma unroll
      for (int D = 0; D < 4; D++) {
        const uint32_t a = fa + (tt == 0 ? 316 : (tt == 1 ? 320 : 0)) + 64 * D;
        f3[tt][D][0] = lds32(a); f3[tt][D][1] = lds32(a + 32); f3[tt][D][2] = lds32(a - 32); f3[tt][D][3] = lds32(a);
      }
  }
    SPLIT();
    nb_sync(NB_GATE, 256);
    SPLIT();
    float a[4][2][4];
#pragma unroll
    for (int kap = 0; kap < 4; kap++)
#pragma unroll
      for (int sg = 0; sg < 2; sg++)
#pragma unroll
        for (int bk = 3; bk >= kap; bk--) {
          const uint32_t(&q0_)[4] = f3[sg ? 2 : 0][bk - kap];
          const uint32_t(&q1_)[4] = f3[sg ? 2 : 1][bk - kap];
          float(&a0)[4] = a[bk][0];
          float(&a1)[4] = a[bk][1];
          if (sg == 0 && kap == 0) {
            mma0(a0[0], a0[1], a0[2], a0[3], q0_[0], q0_[1], q0_[2], q0_[3], z09[0], z09[1]);
            mma0(a1[0], a1[1], a1[2], a1[3], q1_[0], q1_[1], q1_[2], q1_[3], zm9[0], zm9[1]);
          } else {
            mma(a0[0], a0[1], a0[2], a0[3], q0_[0], q0_[1], q0_[2], q0_[3], sg ? zm7[2 * kap] : z09[2 * kap], sg ? zm7[2 * kap + 1] : z09[2 * kap + 1]);
            mma(a1[0], a1[1], a1[2], a1[3], q1_[0], q1_[1], q1_[2], q1_[3], sg ? z07[2 * kap] : zm9[2 * kap], sg ? z07[2 * kap + 1] : zm9[2 * kap + 1]);
          }
        }
    SPLIT();
#pragma unroll
    for (int i = 0; i < 8; i++) {
      uint32_t h[4];
      ldsm4(h, qa + 128 * i);
      const float ci[4] = {a[i >> 1][0][2 * (i & 1)], a[i >> 1][0][2 * (i & 1) + 1], a[i >> 1][1][2 * (i & 1)], a[i >> 1][1][2 * (i & 1) + 1]};
      mmac(acc[8 + i], h[0], h[1], h[2], h[3], lb0, lb1, ci);
    }
  }
  TS(44);
  {
    uint2 a5[10], a3[10];
    const uint32_t aa = tb + T_5 + 4 * (8 + 2 * g - 2 * c);
#pragma unroll
    for (int m = 0; m < 10; m++) { a5[m] = lds64(aa + 32 * m); a3[m] = lds64(aa + 384 + 32 * m); }
    uint32_t x5[12][2], x3[12][2];
    auto ygen = [&](int kap) {
#pragma unroll
      for (int hh = 0; hh < 2; hh++) {
        float y0, y1, y2, y3;
        mma0(y0, y1, y2, y3, by[0], by[1], by[2], by[3], lds32(y0a + 128 * kap + 64 * hh), lds32(y1a + 128 * kap + 64 * hh));
        x5[kap][hh] = pack_bf(y0, y1);
        x3[kap][hh] = pack_bf(y2, y3);
      }
    };
    ygen(11); ygen(10); ygen(9); ygen(8);
#pragma unroll
    for (int kap = 11; kap >= 0; kap--) {
      if (kap >= 4) ygen(kap - 4);
#pragma unroll
      for (int sg = 0; sg < 2; sg++)
#pragma unroll
        for (int i = 4; i >= 0; i--) {
          const int be = kap + 4 + i;
          if (be <= 15) {
            const uint2 &hi = sg ? a3[2 * i + 1] : a5[2 * i + 1], &lo = sg ? a3[2 * i] : a5[2 * i];
            const uint32_t b0 = sg ? x3[kap][0] : x5[kap][0], b1 = sg ? x3[kap][1] : x5[kap][1];
            if (be < 8 && i == 0 && sg == 0) mma0(acc[be][0], acc[be][1], acc[be][2], acc[be][3], hi.x, hi.y, lo.x, lo.y, b0, b1);
            else mma(acc[be][0], acc[be][1], acc[be][2], acc[be][3], hi.x, hi.y, lo.x, lo.y, b0, b1);
          }
        }
    }
  }
  TS(45);
  {
    const uint32_t st = tb + T_ST + lane * 8;
#pragma unroll
    for (int be = 4; be < 12; be++) sts64(st + 256 * be, pack_bf(acc[be][0], acc[be][1]), pack_bf(acc[be][2], acc[be][3]));
    SPLIT();
    uint32_t F[66], qd[8][4];
    const uint32_t fa = tb + T_D + 32 + 4 * x;
#pragma unroll
    for (int i = 0; i < 32; i++) {
      const int s = 120 - (i >> 2) - 8 * (i & 3);
      uint32_t(&q)[4] = qd[i & 7];
      ldsm4(q, qa + 16 * s);
      const int m = 16 * (i & 3) + 2 * (i >> 2);
      F[m] = lds32(fa + 32 * m); F[m + 1] = lds32(fa + 32 * m + 32);
#pragma unroll
      for (int be = 15; be >= 12; be--) {
        const int de = 8 * be - s;
        float(&a)[4] = (be >= 14 && !(i & 1)) ? acc[be - 4] : acc[be];
        if (de >= 0 && be >= 14 && i == 2 * (15 - be)) mma0(a[0], a[1], a[2], a[3], q[0], q[1], q[2], q[3], F[2 * de + 1], F[2 * de]);
        else if (de >= 0) mma(a[0], a[1], a[2], a[3], q[0], q[1], q[2], q[3], F[2 * de + 1], F[2 * de]);
      }
    }
#pragma unroll
    for (int i = 0; i < 8; i++) acc[14 + (i >> 2)][i & 3] += acc[10 + (i >> 2)][i & 3];
    F[64] = lds32(fa + 32 * 64); F[65] = lds32(fa + 32 * 65);
#pragma unroll
    for (int i = 0; i < 6; i++) ldsm4(qd[i], qa + 128 * 11 - 16 * i);
    uint2 sv = lds64(st + 256 * 11);
    float ci[4] = {bf_lo(sv.x), bf_hi(sv.x), bf_lo(sv.y), bf_hi(sv.y)};
    float T[5][4];
#pragma unroll
    for (int i = 0; i < 16; i++) T[i >> 2][i & 3] = acc[12 + (i >> 2)][i & 3];
    nb_sync(NB_YZ, 160);
    TS(46);
    uint32_t held[2];
#pragma unroll
    for (int be = 11; be >= 0; be--) {
      if (be & 1) SPLITN(be);
      const uint32_t qp = qa + 128 * be;
#pragma unroll
      for (int k = 4; k >= 1; k--) mmac(T[k], qd[0][0], qd[0][1], qd[0][2], qd[0][3], F[16 * k + 1], F[16 * k], T[k - 1]);
      if (be >= 4) mmac(T[0], qd[0][0], qd[0][1], qd[0][2], qd[0][3], F[1], F[0], ci);
      else mma0(T[0][0], T[0][1], T[0][2], T[0][3], qd[0][0], qd[0][1], qd[0][2], qd[0][3], F[1], F[0]);
      ldsm4(qd[6], qp - 16 * 6);
      ldsm4(qd[7], qp - 16 * 7);
      if (be > 4) sv = lds64(st + 256 * (be - 1));
#pragma unroll
      for (int i = 1; i < 8; i++) {
#pragma unroll
        for (int k = 3; k >= 0; k--)
          mma(T[k][0], T[k][1], T[k][2], T[k][3], qd[i][0], qd[i][1], qd[i][2], qd[i][3], F[16 * k + 2 * i + 1], F[16 * k + 2 * i]);
        if (i < 7 && be > 0) ldsm4(qd[i - 1], qp - 128 - 16 * (i - 1));
        if (i == 2) {
          const uint32_t w0 = pack_bf(T[4][0], T[4][1]), w1 = pack_bf(T[4][2], T[4][3]);
          if (be & 1) { held[0] = w0; held[1] = w1; }
          else st_x(ydst + (be + 4) * 16, nz(w0), w1, held[0], held[1]);
          if ((be & 3) == 3 && be < 11) nb_arrive(NB_Y + 2 + (be >> 2), 160);
        }
        if (i == 4 && be > 4) { ci[0] = bf_lo(sv.x); ci[1] = bf_hi(sv.x); ci[2] = bf_lo(sv.y); ci[3] = bf_hi(sv.y); }
      }
    }
    nb_arrive(NB_Y + 1, 160);
#pragma unroll
    for (int B = 1; B >= 0; B--)
      st_x(ydst + B * 32, nz(pack_bf(T[2 * B][0], T[2 * B][1])), pack_bf(T[2 * B][2], T[2 * B][3]),
           pack_bf(T[2 * B + 1][0], T[2 * B + 1][1]), pack_bf(T[2 * B + 1][2], T[2 * B + 1][3]));
  }
}

__device__ __forceinline__ void dual_exp(const uint32_t* w, uint32_t* e) {
  const float L = 1.44268798828125f;
  uint32_t mx = bmax2(bmax2(w[0], w[1]), bmax2(w[2], w[3]));
  uint32_t mn = bmin2(bmin2(w[0], w[1]), bmin2(w[2], w[3]));
  mx = bmax2(mx, __shfl_xor_sync(0xffffffffu, mx, 1));
  mn = bmin2(mn, __shfl_xor_sync(0xffffffffu, mn, 1));
  mx = bmax2(mx, __shfl_xor_sync(0xffffffffu, mx, 2));
  mn = bmin2(mn, __shfl_xor_sync(0xffffffffu, mn, 2));
  const float mx0 = bf_lo(mx) * -L, mx1 = bf_hi(mx) * -L, mn0 = bf_lo(mn) * L, mn1 = bf_hi(mn) * L;
#pragma unroll
  for (int i = 0; i < 2; i++) {
    const float a0 = bf_lo(w[2 * i]), a1 = bf_hi(w[2 * i]), b0 = bf_lo(w[2 * i + 1]), b1 = bf_hi(w[2 * i + 1]);
    e[2 * i] = pack_bf(ex2(fmaf(a0, L, mx0)), ex2(fmaf(b0, L, mx0)));
    e[2 * i + 1] = pack_bf(ex2(fmaf(a1, L, mx1)), ex2(fmaf(b1, L, mx1)));
    e[4 + 2 * i] = pack_bf(ex2(fmaf(a0, -L, mn0)), ex2(fmaf(b0, -L, mn0)));
    e[5 + 2 * i] = pack_bf(ex2(fmaf(a1, -L, mn1)), ex2(fmaf(b1, -L, mn1)));
  }
}
__device__ __forceinline__ void normalise(uint32_t* e, const float (&s)[4]) {
  const uint32_t r = pack_bf(rcp(s[0]), rcp(s[2]));
  const __nv_bfloat162 rr = *(const __nv_bfloat162*)&r;
#pragma unroll
  for (int i = 0; i < 4; i++) {
    const __nv_bfloat162 v = __hmul2(*(const __nv_bfloat162*)&e[i], (i & 1) ? __high2bfloat162(rr) : __low2bfloat162(rr));
    e[i] = *(const uint32_t*)&v;
  }
}
__host__ __device__ constexpr uint64_t qdesc(uint32_t addr) { return mkdesc(addr, 128, 256, 0); }

__global__ void __launch_bounds__(NTHREADS, 1)
fused_kernel(const Params P, const __grid_constant__ CUtensorMap mx, const __grid_constant__ CUtensorMap mw,
             const __grid_constant__ CUtensorMap mo, const __grid_constant__ CUtensorMap mu,
             const __grid_constant__ CUtensorMap mout) {
  constexpr uint32_t sb = SB;
  const int tid = threadIdx.x, lane = tid & 31;
  const int warp = __shfl_sync(0xffffffffu, tid >> 5, 0);
  const int b = blockIdx.x, oct = b >> 3, i8 = b & 7;
  const int rt = (((oct & 4) ? ~oct : oct) & 3) * 2 + (i8 >> 2);
  const int hp = (oct >> 2) * 4 + (i8 & 3);

  const int wg = warp >> 2, w = warp & 3;
  const int d = b * 4 + ((tid >> 5) & 3);
  const KgenRaw raw = kgen_load(P, d, (tid >> 7) & 1, lane, (tid + 128) & 256);
  const uint32_t tb = sb + OFF_T + w * T_CH;
  if (warp >= 12) {
    asm volatile("setmaxnreg.dec.sync.aligned.u32 32;");
    if (warp == 12) {
      if (lane == 0) {
#pragma unroll
        for (int i = 0; i < 9; i++) mbar_init(BAR(i), 1);
        asm volatile("fence.mbarrier_init.release.cluster;" ::: "memory");
      }
      __syncwarp();
      if (lane < 9) mbar_expect(BAR(0) + 8 * lane, lane == 0 ? 16384 : 28672);
      __syncwarp();
      nb_arrive(NB_PROD, 384);
#pragma unroll 1
      for (int kb = 0; kb < 8; kb++) {
        if (kb == U_AT) e_tma4d(sb + OFF_STG0, &mu, BAR(MB_URAW), i8 * 64, oct * 2);
        e_tma3d(sb + OFF_W + kb * 12288, &mw, BAR(MB_FULL) + 8 * kb, hp * 32, kb * 64, 0);
        if (kb < 5) e_tma2d(sb + OFF_X + (kb < 2 ? kb + 3 : kb - 2) * 16384, &mx, BAR(MB_FULL) + 8 * kb, kb * 64, rt * 256);
      }
      if (smem_u32(smem_raw) != SB) __trap();
      if (lane == 0) TS1(54);
      nb_sync(NB_GATE + 1, 64);
      e_prefetch(P.x + (size_t)(rt * 256 + 128 + hp * 8) * 512, 8192);
      uint32_t slot = sb + OFF_X + 3 * 16384;
#pragma unroll 1
      for (int n = 0; n < 11; n++) {
        mbar_spin(BAR(MB_EMPTY) + 8 * n);
        const int m = n + 5;
        e_tma2d(slot, &mx, BAR(MB_FULL) + 8 * m, (m & 7) * 64, rt * 256 + (m >> 3) * 128);
        slot = slot == sb + OFF_X + 4 * 16384 ? sb + OFF_X : slot + 16384;
        if (n == 7) {
          e_prefetch(P.wo + (size_t)b * 2048, 4096);
          asm volatile("prefetch.tensormap [%0];" ::"l"(&mo) : "memory");
          asm volatile("prefetch.tensormap [%0];" ::"l"(&mout) : "memory");
        }
      }
#pragma unroll 1
      for (int i = 0; i < 8; i++) {
        mbar_wait(BAR(MB_EMPTY + 10) + 8 * ((0x54332222u >> (4 * i)) & 7));
        const int w0 = (0x54736210u >> (4 * i)) & 7;
        e_tma3d(sb + OFF_W + w0 * 16384, &mo, BAR(MB_WO), 0, w0 * 64, (hp & 3) * 2);
      }
    } else {
      if (warp == 13) {
        if (lane == 0) {
#pragma unroll
          for (int i = 9; i < 40; i++) mbar_init(BAR(i), i < MB_EMPTY ? 1 : 4);
          asm volatile("fence.mbarrier_init.release.cluster;" ::: "memory");
        }
        __syncwarp();
        if (lane < 14 && lane != 9) mbar_expect(BAR(MB_FULL + 8) + 8 * lane, lane == 8 ? 131072 : (lane == 10 ? 8192 : (lane == 13 ? 24576 : 16384)));
        nb_arrive(NB_GATE + 1, 64);
      } else if (warp == 14) {
        asm volatile("prefetch.tensormap [%0];" ::"l"(&mw) : "memory");
        asm volatile("prefetch.tensormap [%0];" ::"l"(&mx) : "memory");
        asm volatile("prefetch.tensormap [%0];" ::"l"(&mu) : "memory");
        e_prefetch(P.x + (size_t)(rt * 256 + hp * 8) * 512, 8192);
      }
      nb_sync(NB_PROD, 384);
      if (warp == 15) {
        const uint4 v0 = __ldg((const uint4*)P.wphi + hp * 64 + lane), v1 = __ldg((const uint4*)P.wphi + hp * 64 + 32 + lane);
        sts128(sb + OFF_PHI + (lane & 1) * 256 + (lane >> 1) * 16, v0.x, v0.y, v0.z, v0.w);
        sts128(sb + OFF_PHI + 512 + (lane & 1) * 256 + (lane >> 1) * 16, v1.x, v1.y, v1.z, v1.w);
        const uint32_t one = (((lane >> 3) ^ (lane >> 4)) & 1) ? 0u : ((lane & 1) ? 0x3F800000u : 0x3F80u);
        const int q = (lane >> 1) & 3;
        sts128(sb + OFF_EYE + lane * 16, q == 0 ? one : 0u, q == 1 ? one : 0u, q == 2 ? one : 0u, q == 3 ? one : 0u);
        sts64(sb + OFF_ONE + lane * 8, 0x3F803F80u, 0x3F803F80u);
        asm volatile("fence.proxy.async.shared::cta;" ::: "memory");
        nb_arrive(NB_KREAD, 160);
      }
      uint32_t* cnt = (uint32_t*)(P.xs + X_CNT) + (warp == 13 ? i8 : (warp == 14 ? 8 + rt : 16 + oct)) * 32;
      const unsigned target = (ld_x32(cnt) & ~15u) + 16;
      if (warp != 14) {
        if (warp == 15) mbar_wait(BAR(MB_EMPTY + ZERO_STEP));
        uint4* pz = P.xs + (warp == 13 ? X_PART + (hp * 8 + rt) * 144 : X_Y + b * 1024) + lane;
#pragma unroll 1
        for (int i = (warp == 13 ? 144 : 1024) - lane; i > 0; i -= 32, pz += 32) st_x(pz, 0, 0, 0, 0);
      }
      if (warp == 15) __syncwarp();
      else nb_sync(warp == 13 ? NB_INIT : NB_ODONE, warp == 13 ? 160 : 288);
      if (lane == 0) asm volatile("red.release.gpu.global.add.u32 [%0], %1;" ::"l"(cnt), "r"(warp == 15 ? 2 : 1) : "memory");
      if (lane == 0) TS1(warp == 13 ? 50 : (warp == 14 ? 57 : 53));
      __syncwarp();
      if (warp == 14) nb_arrive(NB_GATE + 1, 160);
      asm volatile("fence.proxy.async.shared::cta;" ::: "memory");
      if (warp == 13) cnt += ((lane & 1 ? b >> 4 : i8 ^ (lane & 4)) - i8) * 32;
#pragma unroll 1
      for (int i = 0; i < SPIN_MAX; i++) {
        unsigned v;
        asm volatile("ld.acquire.gpu.global.u32 %0, [%1];" : "=r"(v) : "l"(cnt) : "memory");
        if (__all_sync(0xffffffffu, (int)(v - target) >= 0)) break;
      }
      if (lane == 0) TS1(warp == 13 ? 51 : (warp == 14 ? 58 : 55));
      if (warp == 15) { nb_arrive(NB_YZ, 160); return; }
      asm volatile("fence.proxy.async.global;" ::: "memory");
      if (warp == 13) {
        mbar_wait(BAR(MB_EMPTY + 11));
        e_expect(BAR(MB_UFULL), 4 * U_CH);
        e_bulk(sb + OFF_U, P.xs + X_UT + b * (U_CH / 4), 4 * U_CH, BAR(MB_UFULL));
      } else {
        const uint4* src = P.xs + X_O + (rt * 4 + (hp >> 2)) * 4096;
        e_bulk(sb + OFF_X + 32768 + 57344, src + 3584, 8192, BAR(MB_O));
        e_bulk(sb + OFF_X + 32768, src, 16384, BAR(MB_O + 1));
        e_bulk(sb + OFF_X + 49152, src + 1024, 16384, BAR(MB_O + 2));
        e_bulk(sb + OFF_STG0, src + 3200, 6144, BAR(MB_O + 3));
        nb_sync(NB_BDONE, 288);
        asm volatile("fence.proxy.async.shared::cta;" ::: "memory");
        e_bulk(sb + OFF_U, src + 2048, 18432, BAR(MB_O + 3));
      }
    }
    return;
  }

  asm volatile("setmaxnreg.inc.sync.aligned.u32 160;");
  const int t = tid & 127;
  const int g = lane >> 2, c = lane & 3;
  const uint32_t kp = ((tb + 127) & ~127u) + (wg & 1) * 2048;
  const KgenAddr kad = kgen_addr(lane, kp);
  if (wg) nb_sync(NB_PROD, 384);
  float k[5][4], k2048, ksc;
  if (wg) {
    kgen_unit(raw, kad, blockIdx.y, k, k2048, ksc);
    TS(40 + wg);
    if ((fu(k[0][0]) & fu(k[1][0]) & fu(k[2][0]) & fu(k[3][0]) & fu(k[4][0])) == 0xffffffffu) sts32(kp, 0);
  }
  if (wg) nb_arrive(0, 384);
  if (wg) {
    if (wg == 1) {
      uint32_t h[10];
#pragma unroll
      for (int j = 0; j < 10; j++) h[j] = hu(__floats2half2_rn(k[j >> 1][2 * (j & 1)], k[j >> 1][2 * (j & 1) + 1]));
      sts128(kp + lane * 16, h[0], h[1], h[2], h[3]);
      sts128(kp + 512 + lane * 16, h[4], h[5], h[6], h[7]);
      sts128(kp + 1024 + lane * 16, h[8], h[9], fu(k2048), fu(ksc));
      nb_arrive(NB_PREP, 256);
    }
  } else {
    nb_sync(NB_KREAD, 160);
    nb_sync(0, 384);
  }
  if (wg == 1) {
    mbar_wait(BAR(MB_URAW));
    TS(48);
    uint4* dst = P.xs + X_UT + (i8 * 64 + g) * (U_CH / 16) + (w & 1) * (U_ODD / 16) + U_PAD / 16 + oct * 8 + (w >> 1) * 4 + c;
    const int ln = ((lane >> 1) & 3) + 4 * (lane & 1);
    uint32_t r[8][4];
#pragma unroll
    for (int i = 0; i < 8; i++) ldsm4t(r[i], sb + OFF_STG0 + w * 4096 + ((lane >> 3) * 8 + ln) * 128 + ((i ^ ln) << 4));
#pragma unroll
    for (int i = 0; i < 8; i++) dst[i * (U_CH / 2)] = make_uint4(r[i][0], r[i][1], r[i][2], r[i][3]);
    nb_arrive(NB_INIT, 160);
    if (lane == 0) mbar_arrive(BAR(MB_AUX));
  }
  {
    if (wg == 2) {
#pragma unroll
      for (int j = 0; j < 5; j++) { k[j][0] *= ksc; k[j][1] *= ksc; k[j][2] *= ksc; k[j][3] *= ksc; }
      const unsigned short dsk = __ldg((const unsigned short*)P.Dskip + d);
      nb_sync(NB_PREP, 256);
      {
        const uint32_t src = kp + 2048 + lane * 16;
        const uint4 v0 = lds128(src), v1 = lds128(src + 512), v2 = lds128(src + 1024);
        const uint32_t h[10] = {v0.x, v0.y, v0.z, v0.w, v1.x, v1.y, v1.z, v1.w, v2.x, v2.y};
#pragma unroll
        for (int j = 0; j < 10; j++) {
          const float2 f = __half22float2(*(const __half2*)&h[j]);
          k[j >> 1][2 * (j & 1)] = fmaf(f.x, uf(v2.w), k[j >> 1][2 * (j & 1)]);
          k[j >> 1][2 * (j & 1) + 1] = fmaf(f.y, uf(v2.w), k[j >> 1][2 * (j & 1) + 1]);
        }
        k2048 += uf(v2.z);
      }
#pragma unroll
      for (int o2 = 16; o2; o2 >>= 1) k2048 += __shfl_xor_sync(0xffffffffu, k2048, o2);
      if (lane == 0) k[0][0] += bf_lo(dsk);
      __syncwarp();
      TS(34);
      build_tables(tb, lane, k, k2048);
      TS(35);
      uint4* const g_y = P.xs + X_Y;
      conv_channel(sb + OFF_U + w * U_CH, tb, lane, g_y + (size_t)d * 256 + lane);
      nb_arrive(NB_BDONE, 288);
      nb_arrive(NB_Y, 160);
      TS(37);
      if (w == 0) TSDUMP(32);
      return;
    }
    if (wg == 1) {
      mbar_wait(BAR(MB_EMPTY + 4));
      mbar_spin(BAR(MB_EMPTY + 6));
    }
    TS(wg * 16 + 1);
  }

  float acc[2][48];
  {
    uint32_t fb = BAR(MB_FULL) + 64 * wg;
    uint32_t da = (uint32_t)mkdesc(sb + OFF_X, 16, 0, 0) + (wg ? 1024 : 3072), db = (uint32_t)mkdesc(sb + OFF_W, 4096, 0, 0);
    constexpr uint64_t ha = mkdesc(0, 0, 1024, 1), hb = mkdesc(0, 0, 512, 2);
    mbar_spin(fb);
    TS(wg * 16 + 2);
#pragma unroll 1
    for (int kb = 0; kb < 8; kb++) {
      WG_FENCE();
#pragma unroll
      for (int k = 0; k < 4; k++) {
        wgmma_ss_n96(acc[0], ha | (da + 2 * k), hb | (db + 64 * k), k ? 1 : kb);
        wgmma_ss_n96(acc[1], ha | (da + 2 * k + 512), hb | (db + 64 * k), k ? 1 : kb);
      }
      WG_COMMIT();
      if (kb < 7) mbar_spin(fb + 8);
      WG_WAIT(1);
      if (kb > 0) e_arrive(fb + 8 * (MB_EMPTY - MB_FULL - 1));
      fb += 8; db += 768;
      da = da == (uint32_t)mkdesc(sb + OFF_X + 65536, 16, 0, 0) ? da - 4096 : da + 1024;
    }
    WG_WAIT(0);
    e_arrive(fb + 8 * (MB_EMPTY - MB_FULL - 1));
    SPLIT();
  }
  TS(wg * 16 + 3);

  constexpr uint32_t stg0 = sb + OFF_STG0, stg1 = sb + OFF_X + 32768;
  uint4* const g_part = P.xs + X_PART;
  uint4* const g_o = P.xs + X_O;
  constexpr uint32_t kvs = stg0;
  auto pack8 = [](const float* a) { return make_uint4(pack_bf(a[0], a[1]), pack_bf(a[2], a[3]), pack_bf(a[4], a[5]), pack_bf(a[6], a[7])); };
  auto feat = [&](const uint4 (&af)[4], float (&p)[4][8]) {
    WG_FENCE();
#pragma unroll
    for (int u = 0; u < 4; u++) wgmma_rs_n16(p[u], af[u], qdesc(sb + OFF_PHI + (u & 1) * 512), 0);
    WG_COMMIT();
  };
  auto packp = [](const float (&p)[4][8], uint32_t (&pw)[16]) {
#pragma unroll
    for (int i = 0; i < 16; i++) pw[i] = pack_bf(p[i >> 2][(i & 1) + 2 * (i & 2)], p[i >> 2][(i & 1) + 2 * (i & 2) + 2]);
  };
  auto contract = [&](float (&kc)[20], uint32_t stg, int acc_in) {
    WG_FENCE();
#pragma unroll
    for (int s = 0; s < 8; s++) wgmma_ss_n40(kc, qdesc(stg + s * SLAB), qdesc(stg + s * SLAB + 2048), s ? 1 : acc_in);
    WG_COMMIT();
    WG_WAIT(0);
  };
  uint32_t eq[32];
  {
    uint4 af[4], aq[4], vp[4];
    float p[4][8];
#pragma unroll
    for (int u = 0; u < 4; u++) af[u] = pack8(acc[u >> 1] + 16 + 8 * (u & 1));
    feat(af, p);
#pragma unroll
    for (int u = 0; u < 4; u++) { aq[u] = pack8(acc[u >> 1] + 8 * (u & 1)); vp[u] = pack8(acc[u >> 1] + 32 + 8 * (u & 1)); }
    WG_WAIT(0);
    uint32_t pw[16], ek[32];
    packp(p, pw);
#pragma unroll
    for (int u = 0; u < 4; u++) dual_exp(pw + 4 * u, ek + 8 * u);
    TS(wg * 16 + 12);
    mbar_spin(wg ? BAR(MB_EMPTY + 15) : BAR(MB_AUX));
    float rs[8][4];
    WG_FENCE();
#pragma unroll
    for (int i = 0; i < 8; i++) wgmma_rs_n8(rs[i], make_uint4(ek[4 * i], ek[4 * i + 1], ek[4 * i + 2], ek[4 * i + 3]), qdesc(sb + OFF_ONE), 0);
    WG_COMMIT();
    feat(aq, p);
    const uint32_t sl = (wg ? stg1 : stg0) + w * SLAB + lane * 16;
#pragma unroll
    for (int i = 0; i < 4; i++) stsm4(sl + (i >> 1) * 4 * SLAB + 2048 + (i & 1) * 512, vp[i].x, vp[i].y, vp[i].z, vp[i].w);
    sts128(sl + (lane >> 4) * (4 * SLAB - 256) + 3072, 0x3F803F80u, 0x3F803F80u, 0x3F803F80u, 0x3F803F80u);
    WG_WAIT(1);
#pragma unroll
    for (int i = 0; i < 8; i++) {
      normalise(ek + 4 * i, rs[i]);
      stsm4(sl + (i >> 2) * 4 * SLAB + (i & 3) * 512, ek[4 * i], ek[4 * i + 1], ek[4 * i + 2], ek[4 * i + 3]);
    }
    asm volatile("fence.proxy.async.shared::cta;" ::: "memory");
    TS(wg * 16 + 13);
    if (wg) {
      nb_arrive(NB_ST0, 256);
      nb_arrive(NB_GATE, 256);
    } else {
      float kc[20];
      uint4* pp = g_part + (size_t)(hp * 8 + rt) * 144 + t;
      uint32_t* pz = (uint32_t*)(pp - t + 128) + w * 16 + c * 8 + g;
      asm volatile("" : "+l"(pp), "+l"(pz));
      nb_sync(NB_WG0, 128);
      contract(kc, stg0, 0);
      mbar_wait(BAR(MB_UFULL));
      TS(15);
      nb_sync(NB_ST0, 256);
      contract(kc, stg1, 1);
      TS(6);
      float kv[8];
#pragma unroll
      for (int i = 0; i < 8; i++) kv[i] = w & 2 ? kc[8 + i] : kc[i];
      st_x(pp, nz(pack_bf(kv[0], kv[1])), pack_bf(kv[2], kv[3]), pack_bf(kv[4], kv[5]), pack_bf(kv[6], kv[7]));
      if (c < 2) st_x32(pz, nz(fu(c ? kc[18] : kc[16])));
      TS(5);
    }
    SPLIT();
    WG_WAIT(0);
    packp(p, pw);
#pragma unroll
    for (int u = 0; u < 4; u++) dual_exp(pw + 4 * u, eq + 8 * u);
    SPLIT();
  }
  TS(wg * 16 + 4);
  if (wg == 1) {
    mbar_wait(BAR(MB_UFULL));
    const uint4* ps = g_part + (size_t)hp * 8 * 144 + t;
    const uint32_t* zs = (const uint32_t*)(g_part + (size_t)(hp * 8 + (lane >> 4) * 4) * 144 + 128) + w * 16 + (lane & 15);
    uint4 v[8];
    uint32_t zv[4];
#pragma unroll 1
    for (int it = 0; it < SPIN_MAX; it++) {
#pragma unroll
      for (int i = 0; i < 8; i++) v[i] = ld_x(ps + i * 144);
#pragma unroll
      for (int i = 0; i < 4; i++) zv[i] = ld_x32(zs + i * 576);
      uint32_t m = min(min(zv[0], zv[1]), min(zv[2], zv[3]));
#pragma unroll
      for (int i = 0; i < 8; i++) m = min(m, v[i].x);
      if (__all_sync(0xffffffffu, m != 0)) break;
    }
    float s[8];
    WG_FENCE();
#pragma unroll
    for (int r = 0; r < 8; r++) wgmma_rs_n16(s, v[r], qdesc(sb + OFF_EYE), r);
    WG_COMMIT();
    float zsum = (uf(zv[0]) + uf(zv[1])) + (uf(zv[2]) + uf(zv[3]));
    zsum += __shfl_xor_sync(0xffffffffu, zsum, 16);
    const uint32_t z1 = pack_bf(zsum, 1.f);
    if (lane < 16) sts128(kvs + w * 768 + 512 + lane * 16, z1, z1, z1, z1);
    WG_WAIT(0);
    stsm4(kvs + w * 768 + lane * 16, pack_bf(s[0], s[1]), pack_bf(s[2], s[3]), pack_bf(s[4], s[5]), pack_bf(s[6], s[7]));
    asm volatile("fence.proxy.async.shared::cta;" ::: "memory");
    TS(22);
  }
  nb_sync(NB_KV, 256);
  {
    float n[8][12];
    WG_FENCE();
#pragma unroll
    for (int i = 0; i < 8; i++) wgmma_rs_n24(n[i], make_uint4(eq[4 * i], eq[4 * i + 1], eq[4 * i + 2], eq[4 * i + 3]), qdesc(kvs + (i & 3) * 768), 0);
    WG_COMMIT();
    uint32_t* od = (uint32_t*)(g_o + (size_t)((rt * 4 + wg * 2) * 32 + hp * 2) * 128) + w * 64 + lane;
    WG_WAIT(0);
#pragma unroll
    for (int u = 0; u < 4; u++) {
      float(&np)[12] = n[2 * u];
      const float(&nm)[12] = n[2 * u + 1];
      const float q0 = np[9] * rcp(nm[9]), q1 = np[11] * rcp(nm[11]);
      const float r0 = rcp(fmaf(nm[8], q0, fmaf(np[9], 1e-6f, np[8]))), r1 = rcp(fmaf(nm[10], q1, fmaf(np[11], 1e-6f, np[10])));
#pragma unroll
      for (int i = 0; i < 8; i++) np[i] = fmaf(nm[i], (i & 2) ? q1 : q0, np[i]);
      uint32_t* o = od + (u >> 1) * 16384 + (u & 1) * 512;
      o[0] = pack_bf(np[0] * r0, np[1] * r0);
      o[32] = pack_bf(np[2] * r1, np[3] * r1);
      o[256] = pack_bf(np[4] * r0, np[5] * r0);
      o[288] = pack_bf(np[6] * r1, np[7] * r1);
      if (u == 1) SPLIT();
    }
  }
  TS(wg * 16 + 7);
  nb_arrive(NB_ODONE, 288);
  if (wg) {
    const uint4* src = P.xs + X_Y + (oct * 32 + c * 8) * 256 + (2 * w + (g >> 2)) * 32 + i8 * 4 + (g & 3);
    __nv_bfloat16* dst = P.out + (size_t)((2 * w + (g >> 2)) * 256 + i8 * 16 + (g & 3) * 2) * 1024 + 512 + oct * 32 + c * 8;
    nb_sync(NB_GATE + 1, 160);
    nb_sync(NB_Y + w, 160);
    uint4 v[8];
#pragma unroll 1
    for (int it = 0; it < SPIN_MAX; it++) {
      uint32_t m = 0xffffffffu;
#pragma unroll
      for (int i = 0; i < 8; i++) v[i] = ld_x(src + i * 256);
#pragma unroll
      for (int i = 0; i < 8; i++) m = min(m, v[i].x);
      if (__all_sync(0xffffffffu, m != 0)) break;
    }
#pragma unroll
    for (int i = 0; i < 8; i++) *(uint4*)(dst + (size_t)((i >> 2) * 128 + ((i >> 1) & 1) * 8 + (i & 1)) * 1024) = tr_row(v, i);
    TS(31);
    GT(63);
    if (w == 0) TSDUMP(16);
    return;
  }
  mbar_wait(BAR(MB_WO));
  nb_sync(NB_BDONE, 288);
  TS(8);
  mbar_spin(BAR(MB_O));
  TS(9);
  constexpr uint64_t ha = mkdesc(0, 0, 128, 0), hb = mkdesc(0, 0, 1024, 1);
  constexpr uint32_t da0 = (uint32_t)mkdesc(stg1, 1024, 0, 0), db0 = (uint32_t)mkdesc(sb + OFF_W, 8192, 0, 0);
  const uint32_t ot = ((sb + OFF_T + 1023) & ~1023u) + w * 4096;
  auto store_half = [&](const float* oc, int hf) {
#pragma unroll
    for (int i = 0; i < 8; i += 2)
      stsm4(ot + hf * 2048 + (lane & 15) * 128 + (((i + (lane >> 4)) ^ lane) & 7) * 16, pack_bf(oc[4 * i], oc[4 * i + 1]),
            pack_bf(oc[4 * i + 2], oc[4 * i + 3]), pack_bf(oc[4 * i + 4], oc[4 * i + 5]), pack_bf(oc[4 * i + 6], oc[4 * i + 7]));
    asm volatile("fence.proxy.async.shared::cta;" ::: "memory");
    __syncwarp();
    e_store2d(&mout, ot + hf * 2048, (hp & 3) * 128 + hf * 64, (rt * 4 + (hp >> 2)) * 64 + w * 16);
  };
  float oc[64];
#pragma unroll 1
  for (int j = 0; j < 8; j++) {
    const int kb = (j + 7) & 7;
    if ((j & 1) && j < 6) mbar_spin(BAR(MB_O + 1) + 4 * (j - 1));
    WG_FENCE();
#pragma unroll
    for (int k = 0; k < 4; k++) wgmma_ss_n128(oc, ha | (da0 + 512 * kb + 128 * k), hb | (db0 + 1024 * kb + 128 * k), k ? 1 : j);
    WG_COMMIT();
  }
  WG_WAIT(0);
  TS(10);
  store_half(oc, 0);
  store_half(oc + 32, 1);
  asm volatile(ELECT "cp.async.bulk.commit_group;\n@p cp.async.bulk.wait_group.read 0;\n}\n" ::: "memory");
  TS(wg * 16 + 11);
  GT(61 + wg);
  if (w == 0) TSDUMP(0);
  if (w == 1) TSDUMP(48);
}

typedef CUresult (*EncodeFn)(CUtensorMap*, CUtensorMapDataType, cuuint32_t, void*, const cuuint64_t*, const cuuint64_t*,
                             const cuuint32_t*, const cuuint32_t*, CUtensorMapInterleave, CUtensorMapSwizzle,
                             CUtensorMapL2promotion, CUtensorMapFloatOOBfill);

}

extern "C" void kernel_launch(void* const* d_in, const int* in_sizes, int n_in, void* d_out, int out_size) {
  (void)in_sizes; (void)n_in; (void)out_size;
  void* fn = nullptr;
  cudaDriverEntryPointQueryResult qr;
  cudaGetDriverEntryPoint("cuTensorMapEncodeTiled", &fn, cudaEnableDefault, &qr);
  EncodeFn enc = (EncodeFn)fn;
  CUtensorMap mx, mw, mo, mu, mout;
  const cuuint32_t es[5] = {1, 1, 1, 1, 1};
  {
    cuuint64_t dims[2] = {512, 2048}, st[1] = {1024};
    cuuint32_t box[2] = {64, 128};
    enc(&mx, CU_TENSOR_MAP_DATA_TYPE_BFLOAT16, 2, d_in[0], dims, st, box, es, CU_TENSOR_MAP_INTERLEAVE_NONE,
        CU_TENSOR_MAP_SWIZZLE_128B, CU_TENSOR_MAP_L2_PROMOTION_L2_128B, CU_TENSOR_MAP_FLOAT_OOB_FILL_NONE);
  }
  {
    cuuint64_t dims[3] = {512, 512, 3}, st[2] = {3072, 1024};
    cuuint32_t box[3] = {32, 64, 3};
    enc(&mw, CU_TENSOR_MAP_DATA_TYPE_BFLOAT16, 3, d_in[1], dims, st, box, es, CU_TENSOR_MAP_INTERLEAVE_NONE,
        CU_TENSOR_MAP_SWIZZLE_64B, CU_TENSOR_MAP_L2_PROMOTION_L2_128B, CU_TENSOR_MAP_FLOAT_OOB_FILL_NONE);
  }
  {
    cuuint64_t dims[3] = {64, 512, 8}, st[2] = {1024, 128};
    cuuint32_t box[3] = {64, 64, 2};
    enc(&mo, CU_TENSOR_MAP_DATA_TYPE_BFLOAT16, 3, d_in[3], dims, st, box, es, CU_TENSOR_MAP_INTERLEAVE_NONE,
        CU_TENSOR_MAP_SWIZZLE_128B, CU_TENSOR_MAP_L2_PROMOTION_L2_128B, CU_TENSOR_MAP_FLOAT_OOB_FILL_NONE);
  }
  {
    cuuint64_t dims[4] = {512, 4, 16, 32}, st[3] = {16384, 1024, 65536};
    cuuint32_t box[4] = {64, 4, 16, 2};
    enc(&mu, CU_TENSOR_MAP_DATA_TYPE_BFLOAT16, 4, d_in[4], dims, st, box, es, CU_TENSOR_MAP_INTERLEAVE_NONE,
        CU_TENSOR_MAP_SWIZZLE_128B, CU_TENSOR_MAP_L2_PROMOTION_L2_128B, CU_TENSOR_MAP_FLOAT_OOB_FILL_NONE);
  }
  {
    cuuint64_t dims[2] = {1024, 2048}, st[1] = {2048};
    cuuint32_t box[2] = {64, 16};
    enc(&mout, CU_TENSOR_MAP_DATA_TYPE_BFLOAT16, 2, d_out, dims, st, box, es, CU_TENSOR_MAP_INTERLEAVE_NONE,
        CU_TENSOR_MAP_SWIZZLE_128B, CU_TENSOR_MAP_L2_PROMOTION_NONE, CU_TENSOR_MAP_FLOAT_OOB_FILL_NONE);
  }
  Params P;
  P.x = (const __nv_bfloat16*)d_in[0];
  P.wphi = (const __nv_bfloat16*)d_in[2];
  P.wo = (const __nv_bfloat16*)d_in[3];
  P.logA = (const __nv_bfloat16*)d_in[5];
  P.Aim = (const __nv_bfloat16*)d_in[6];
  P.Cre = (const __nv_bfloat16*)d_in[7];
  P.Cim = (const __nv_bfloat16*)d_in[8];
  P.logdt = (const __nv_bfloat16*)d_in[9];
  P.Dskip = (const __nv_bfloat16*)d_in[10];
  P.out = (__nv_bfloat16*)d_out;
  cudaGetSymbolAddress((void**)&P.xs, g_x);
  P.ts = nullptr;
  cudaFuncSetAttribute(fused_kernel, cudaFuncAttributeMaxDynamicSharedMemorySize, SMEM_BYTES);
  fused_kernel<<<NCTA, NTHREADS, SMEM_BYTES>>>(P, mx, mw, mo, mu, mout);
}
```

```cpp
#include <cuda_runtime.h>
#include <cuda_bf16.h>
#include <cuda_fp16.h>
#include <cuda.h>
#include <stdint.h>
#include <type_traits>

#define DBG_TS 0

namespace {

constexpr int NTHREADS = 512;
constexpr int NCTA = 128;
constexpr int OFF_W = 0;
constexpr int OFF_X = 98304;
constexpr int OFF_U = OFF_X + 65536;
constexpr int U_CH = 4416, U_ODD = 2240, U_PAD = 128;
constexpr int OFF_STG0 = OFF_U + 18432;
constexpr int SLAB = 3328;
constexpr int OFF_T = OFF_STG0 + 8 * SLAB;
constexpr int T_CH = 5216;
constexpr int T_D = 0;
constexpr int T_5 = 2144;
constexpr int T_3 = T_5 + 384;
constexpr int T_7 = T_5 + 1024;
constexpr int T_9 = T_7 + 320;
constexpr int T_KC = T_9 + 320;
constexpr int T_ST = T_5 - 1024;
constexpr int OFF_PHI = OFF_T + 4 * T_CH;
constexpr int OFF_EYE = OFF_PHI + 1024, OFF_ONE = OFF_EYE + 512;
constexpr int OFF_BAR = OFF_ONE + 256;
constexpr int SMEM_BYTES = OFF_BAR + 512 + 256 * DBG_TS;
constexpr uint32_t SB = 1024;
static_assert(T_KC + 2 * 656 <= T_CH, "table size");
static_assert(SMEM_BYTES <= 232448, "smem");
constexpr int MB_URAW = 0, MB_FULL = 1  , MB_WO = 17, MB_UFULL = 18, MB_O = 19  ,
              MB_EMPTY = 23  , MB_AUX = 39;
__host__ __device__ constexpr uint32_t BAR(int i) { return SB + OFF_BAR + 8 * i; }
constexpr int NB_WG0 = 1, NB_ODONE = 2, NB_ST0 = 3, NB_HAND = 4, NB_KV = 5, NB_YZ = 6, NB_INIT = 7, NB_PREP = 8, NB_PROD = 9, NB_KREAD = 10,
              NB_BDONE = 11, NB_GATE = 12  , NB_Y = 7  ;
constexpr int U_AT = 2;
constexpr int ZERO_STEP = 12;
constexpr int SPIN_MAX = 1 << 16;

constexpr int X_CNT = 0;
constexpr int X_PART = 256;
constexpr int X_O = X_PART + 16 * 8 * 144;
constexpr int X_Y = X_O + 32 * 32 * 128;
constexpr int X_UT = X_Y + 512 * 8 * 32;
constexpr int X_SIZE = X_UT + 512 * (U_CH / 16);
__device__ __align__(128) uint4 g_x[X_SIZE];
extern __shared__ uint8_t smem_raw[];
#define TS(i) do {} while (0)
#define TS1(i) do {} while (0)
#define GT(i) do {} while (0)
#define TSDUMP(base) do {} while (0)

__device__ __forceinline__ uint32_t smem_u32(const void* p) { return (uint32_t)__cvta_generic_to_shared(p); }
__device__ __forceinline__ void mbar_arrive(uint32_t b) {
  asm volatile("mbarrier.arrive.shared::cta.b64 _, [%0];" ::"r"(b) : "memory");
}
__device__ __forceinline__ void mbar_wait(uint32_t b) {
  uint32_t done = 0;
#pragma unroll 1
  for (int i = 0; i < SPIN_MAX && !done; i++) {
    asm volatile("{\n.reg .pred p;\nmbarrier.try_wait.parity.shared::cta.b64 p, [%1], 0, 4000;\nselp.u32 %0, 1, 0, p;\n}\n"
                 : "=r"(done) : "r"(b) : "memory");
  }
}
__device__ __forceinline__ void mbar_spin(uint32_t b) {
  uint32_t done = 0;
#pragma unroll 1
  for (int i = 0; i < (SPIN_MAX << 4) && !done; i++) {
    asm volatile("{\n.reg .pred p;\nmbarrier.try_wait.parity.shared::cta.b64 p, [%1], 0;\nselp.u32 %0, 1, 0, p;\n}\n"
                 : "=r"(done) : "r"(b) : "memory");
  }
}
__device__ __forceinline__ void mbar_init(uint32_t b, int n) {
  asm volatile("mbarrier.init.shared::cta.b64 [%0], %1;" ::"r"(b), "r"(n) : "memory");
}
__device__ __forceinline__ void mbar_expect(uint32_t b, int bytes) {
  asm volatile("mbarrier.arrive.expect_tx.shared::cta.b64 _, [%0], %1;" ::"r"(b), "r"(bytes) : "memory");
}
__device__ __forceinline__ void nb_sync(int id, int n) { asm volatile("bar.sync %0, %1;" ::"r"(id), "r"(n) : "memory"); }
__device__ __forceinline__ void nb_arrive(int id, int n) { asm volatile("bar.arrive %0, %1;" ::"r"(id), "r"(n) : "memory"); }
#define ELECT "{\n.reg .pred p;\nelect.sync _|p, 0xffffffff;\n@p "
__device__ __forceinline__ void e_arrive(uint32_t b) {
  asm volatile(ELECT "mbarrier.arrive.shared::cta.b64 _, [%0];\n}\n" ::"r"(b) : "memory");
}
__device__ __forceinline__ void e_expect(uint32_t b, int bytes) {
  asm volatile(ELECT "mbarrier.arrive.expect_tx.shared::cta.b64 _, [%0], %1;\n}\n" ::"r"(b), "r"(bytes) : "memory");
}
__device__ __forceinline__ void e_tma2d(uint32_t dst, const CUtensorMap* m, uint32_t bar, int c0, int c1) {
  asm volatile(ELECT "cp.async.bulk.tensor.2d.shared::cluster.global.mbarrier::complete_tx::bytes [%0], [%1, {%3,%4}], [%2];\n}\n"
               ::"r"(dst), "l"(m), "r"(bar), "r"(c0), "r"(c1) : "memory");
}
__device__ __forceinline__ void e_tma3d(uint32_t dst, const CUtensorMap* m, uint32_t bar, int c0, int c1, int c2) {
  asm volatile(ELECT "cp.async.bulk.tensor.3d.shared::cluster.global.mbarrier::complete_tx::bytes [%0], [%1, {%3,%4,%5}], [%2];\n}\n"
               ::"r"(dst), "l"(m), "r"(bar), "r"(c0), "r"(c1), "r"(c2) : "memory");
}
__device__ __forceinline__ void e_tma4d(uint32_t dst, const CUtensorMap* m, uint32_t bar, int c0, int c3) {
  asm volatile(ELECT "cp.async.bulk.tensor.4d.shared::cluster.global.mbarrier::complete_tx::bytes [%0], [%1, {%3,%5,%5,%4}], [%2];\n}\n"
               ::"r"(dst), "l"(m), "r"(bar), "r"(c0), "r"(c3), "r"(0) : "memory");
}
__device__ __forceinline__ void e_bulk(uint32_t dst, const void* src, int bytes, uint32_t bar) {
  asm volatile(ELECT "cp.async.bulk.shared::cluster.global.mbarrier::complete_tx::bytes [%0], [%1], %2, [%3];\n}\n"
               ::"r"(dst), "l"(src), "r"(bytes), "r"(bar) : "memory");
}
__device__ __forceinline__ void e_prefetch(const void* p, int bytes) {
  asm volatile(ELECT "cp.async.bulk.prefetch.L2.global [%0], %1;\n}\n" ::"l"(p), "r"(bytes) : "memory");
}
__device__ __forceinline__ void e_store2d(const CUtensorMap* m, uint32_t src, int c0, int c1) {
  asm volatile(ELECT "cp.async.bulk.tensor.2d.global.shared::cta.bulk_group [%0, {%2,%3}], [%1];\n}\n"
               ::"l"(m), "r"(src), "r"(c0), "r"(c1) : "memory");
}
__host__ __device__ constexpr uint64_t mkdesc(uint32_t addr, uint32_t lbo, uint32_t sbo, int swz) {
  return (uint64_t)((addr & 0x3FFFF) >> 4) | ((uint64_t)(lbo >> 4) << 16) | ((uint64_t)(sbo >> 4) << 32) |
         ((uint64_t)swz << 62);
}
#define SPLIT() asm volatile("{\n.reg .pred p;\nsetp.eq.u32 p, %0, %1;\n@p exit;\n}\n" ::"r"(blockIdx.y), "n"(__LINE__) : "memory")
#define SPLITN(n) asm volatile("{\n.reg .pred p;\nsetp.eq.u32 p, %0, %1;\n@p exit;\n}\n" ::"r"(blockIdx.y), "r"(4096 + (n)) : "memory")
#define WG_FENCE() asm volatile("wgmma.fence.sync.aligned;" ::: "memory")
#define WG_COMMIT() asm volatile("wgmma.commit_group.sync.aligned;" ::: "memory")
#define WG_WAIT(n) asm volatile("wgmma.wait_group.sync.aligned " #n ";" ::: "memory")

__device__ __forceinline__ void mma(float& d0, float& d1, float& d2, float& d3, uint32_t a0, uint32_t a1, uint32_t a2,
                                    uint32_t a3, uint32_t b0, uint32_t b1) {
  asm volatile("mma.sync.aligned.m16n8k16.row.col.f32.bf16.bf16.f32 {%0,%1,%2,%3},{%4,%5,%6,%7},{%8,%9},{%0,%1,%2,%3};"
               : "+f"(d0), "+f"(d1), "+f"(d2), "+f"(d3)
               : "r"(a0), "r"(a1), "r"(a2), "r"(a3), "r"(b0), "r"(b1));
}
__device__ __forceinline__ void mmac(float (&d)[4], uint32_t a0, uint32_t a1, uint32_t a2, uint32_t a3, uint32_t b0,
                                     uint32_t b1, const float (&c)[4]) {
  asm volatile("mma.sync.aligned.m16n8k16.row.col.f32.bf16.bf16.f32 {%0,%1,%2,%3},{%4,%5,%6,%7},{%8,%9},{%10,%11,%12,%13};"
               : "=f"(d[0]), "=f"(d[1]), "=f"(d[2]), "=f"(d[3])
               : "r"(a0), "r"(a1), "r"(a2), "r"(a3), "r"(b0), "r"(b1), "f"(c[0]), "f"(c[1]), "f"(c[2]), "f"(c[3]));
}
__device__ __forceinline__ void mma_h(float (&d)[4], const uint32_t (&a)[4], uint32_t b0, uint32_t b1) {
  asm volatile("mma.sync.aligned.m16n8k16.row.col.f32.f16.f16.f32 {%0,%1,%2,%3},{%4,%5,%6,%7},{%8,%9},{%0,%1,%2,%3};"
               : "+f"(d[0]), "+f"(d[1]), "+f"(d[2]), "+f"(d[3]) : "r"(a[0]), "r"(a[1]), "r"(a[2]), "r"(a[3]), "r"(b0), "r"(b1));
}
__device__ __forceinline__ void mma0(float& d0, float& d1, float& d2, float& d3, uint32_t a0, uint32_t a1, uint32_t a2,
                                     uint32_t a3, uint32_t b0, uint32_t b1) {
  asm volatile("mma.sync.aligned.m16n8k16.row.col.f32.bf16.bf16.f32 {%0,%1,%2,%3},{%4,%5,%6,%7},{%8,%9},{%10,%10,%10,%10};"
               : "=f"(d0), "=f"(d1), "=f"(d2), "=f"(d3)
               : "r"(a0), "r"(a1), "r"(a2), "r"(a3), "r"(b0), "r"(b1), "f"(0.f));
}
__device__ __forceinline__ uint32_t pack_bf(float lo, float hi) {
  uint32_t r;
  asm("cvt.rn.bf16x2.f32 %0, %1, %2;" : "=r"(r) : "f"(hi), "f"(lo));
  return r;
}
__device__ __forceinline__ float bf_lo(uint32_t w) { return __uint_as_float(w << 16); }
__device__ __forceinline__ float bf_hi(uint32_t w) { return __uint_as_float(w & 0xffff0000u); }
__device__ __forceinline__ float bf_round(float x) { return __bfloat162float(__float2bfloat16_rn(x)); }
__device__ __forceinline__ uint32_t bmax2(uint32_t a, uint32_t b) {
  uint32_t r; asm("max.bf16x2 %0, %1, %2;" : "=r"(r) : "r"(a), "r"(b)); return r;
}
__device__ __forceinline__ uint32_t bmin2(uint32_t a, uint32_t b) {
  uint32_t r; asm("min.bf16x2 %0, %1, %2;" : "=r"(r) : "r"(a), "r"(b)); return r;
}
__device__ __forceinline__ float ex2(float x) { float r; asm("ex2.approx.ftz.f32 %0, %1;" : "=f"(r) : "f"(x)); return r; }
__device__ __forceinline__ float rcp(float x) { float r; asm("rcp.approx.ftz.f32 %0, %1;" : "=f"(r) : "f"(x)); return r; }
__device__ __forceinline__ void ldsm4(uint32_t (&r)[4], uint32_t a) {
  asm volatile("ldmatrix.sync.aligned.m8n8.x4.shared.b16 {%0,%1,%2,%3}, [%4];"
               : "=r"(r[0]), "=r"(r[1]), "=r"(r[2]), "=r"(r[3]) : "r"(a) : "memory");
}
__device__ __forceinline__ void ldsm4t(uint32_t (&r)[4], uint32_t a) {
  asm volatile("ldmatrix.sync.aligned.m8n8.x4.trans.shared.b16 {%0,%1,%2,%3}, [%4];"
               : "=r"(r[0]), "=r"(r[1]), "=r"(r[2]), "=r"(r[3]) : "r"(a) : "memory");
}
__device__ __forceinline__ void stsm4(uint32_t a, uint32_t r0, uint32_t r1, uint32_t r2, uint32_t r3) {
  asm volatile("stmatrix.sync.aligned.m8n8.x4.shared.b16 [%0], {%1,%2,%3,%4};"
               ::"r"(a), "r"(r0), "r"(r1), "r"(r2), "r"(r3) : "memory");
}
__device__ __forceinline__ uint32_t lds32(uint32_t a) {
  uint32_t r; asm volatile("ld.shared.u32 %0, [%1];" : "=r"(r) : "r"(a) : "memory"); return r;
}
__device__ __forceinline__ uint32_t lds16(uint32_t a) {
  uint32_t r; asm volatile("{\n.reg .u16 h;\nld.shared.u16 h, [%1];\ncvt.u32.u16 %0, h;\n}\n" : "=r"(r) : "r"(a) : "memory"); return r;
}
__device__ __forceinline__ uint2 lds64(uint32_t a) {
  uint2 r; asm volatile("ld.shared.v2.u32 {%0,%1}, [%2];" : "=r"(r.x), "=r"(r.y) : "r"(a) : "memory"); return r;
}
__device__ __forceinline__ uint4 lds128(uint32_t a) {
  uint4 r;
  asm volatile("ld.shared.v4.u32 {%0,%1,%2,%3}, [%4];" : "=r"(r.x), "=r"(r.y), "=r"(r.z), "=r"(r.w) : "r"(a) : "memory");
  return r;
}
__device__ __forceinline__ void sts32(uint32_t a, uint32_t v) { asm volatile("st.shared.u32 [%0], %1;" ::"r"(a), "r"(v) : "memory"); }
__device__ __forceinline__ void sts16(uint32_t a, uint32_t v) {
  asm volatile("{\n.reg .u16 h;\ncvt.u16.u32 h, %1;\nst.shared.u16 [%0], h;\n}\n" ::"r"(a), "r"(v) : "memory");
}
__device__ __forceinline__ void sts64(uint32_t a, uint32_t x, uint32_t y) {
  asm volatile("st.shared.v2.u32 [%0], {%1,%2};" ::"r"(a), "r"(x), "r"(y) : "memory");
}
__device__ __forceinline__ void sts128(uint32_t a, uint32_t x, uint32_t y, uint32_t z, uint32_t w) {
  asm volatile("st.shared.v4.u32 [%0], {%1,%2,%3,%4};" ::"r"(a), "r"(x), "r"(y), "r"(z), "r"(w) : "memory");
}
__device__ __forceinline__ uint4 ld_x(const uint4* p) {
  uint4 r;
  asm volatile("{\n.reg .b128 t;\nld.relaxed.gpu.global.b128 t, [%4];\nmov.b128 {%0,%1,%2,%3}, t;\n}\n"
               : "=r"(r.x), "=r"(r.y), "=r"(r.z), "=r"(r.w) : "l"(p) : "memory");
  return r;
}
__device__ __forceinline__ uint32_t ld_x32(const uint32_t* p) {
  uint32_t r; asm volatile("ld.relaxed.gpu.global.u32 %0, [%1];" : "=r"(r) : "l"(p) : "memory"); return r;
}
__device__ __forceinline__ void st_x(uint4* p, uint32_t x, uint32_t y, uint32_t z, uint32_t w) {
  asm volatile("{\n.reg .b128 t;\nmov.b128 t, {%1,%2,%3,%4};\nst.relaxed.gpu.global.b128 [%0], t;\n}\n"
               ::"l"(p), "r"(x), "r"(y), "r"(z), "r"(w) : "memory");
}
__device__ __forceinline__ void st_x32(uint32_t* p, uint32_t x) {
  asm volatile("st.relaxed.gpu.global.u32 [%0], %1;" ::"l"(p), "r"(x) : "memory");
}
__device__ __forceinline__ uint32_t nz(uint32_t w) { return max(w, 1u); }
__device__ __forceinline__ uint32_t fu(float x) { return __float_as_uint(x); }
__device__ __forceinline__ float uf(uint32_t x) { return __uint_as_float(x); }

__device__ __forceinline__ void wgmma_ss_n96(float (&d)[48], uint64_t da, uint64_t db, int sc) {
  asm volatile("{\n.reg .pred p;\nsetp.ne.b32 p, %50, 0;\n"
      "wgmma.mma_async.sync.aligned.m64n96k16.f32.bf16.bf16 "
      "{%0,%1,%2,%3,%4,%5,%6,%7,%8,%9,%10,%11,%12,%13,%14,%15,%16,%17,%18,%19,%20,%21,%22,%23,%24,%25,%26,%27,%28,%29,%30,%31,%32,%33,%34,%35,%36,%37,%38,%39,%40,%41,%42,%43,%44,%45,%46,%47}, "
      "%48, %49, p, 1, 1, 0, 1;\n}\n"
      : "+f"(d[0]), "+f"(d[1]), "+f"(d[2]), "+f"(d[3]), "+f"(d[4]), "+f"(d[5]), "+f"(d[6]), "+f"(d[7]),
        "+f"(d[8]), "+f"(d[9]), "+f"(d[10]), "+f"(d[11]), "+f"(d[12]), "+f"(d[13]), "+f"(d[14]), "+f"(d[15]),
        "+f"(d[16]), "+f"(d[17]), "+f"(d[18]), "+f"(d[19]), "+f"(d[20]), "+f"(d[21]), "+f"(d[22]), "+f"(d[23]),
        "+f"(d[24]), "+f"(d[25]), "+f"(d[26]), "+f"(d[27]), "+f"(d[28]), "+f"(d[29]), "+f"(d[30]), "+f"(d[31]),
        "+f"(d[32]), "+f"(d[33]), "+f"(d[34]), "+f"(d[35]), "+f"(d[36]), "+f"(d[37]), "+f"(d[38]), "+f"(d[39]),
        "+f"(d[40]), "+f"(d[41]), "+f"(d[42]), "+f"(d[43]), "+f"(d[44]), "+f"(d[45]), "+f"(d[46]), "+f"(d[47])
      : "l"(da), "l"(db), "r"(sc));
}

__device__ __forceinline__ void wgmma_ss_n128(float (&d)[64], uint64_t da, uint64_t db, int sc) {
  asm volatile("{\n.reg .pred p;\nsetp.ne.b32 p, %66, 0;\n"
      "wgmma.mma_async.sync.aligned.m64n128k16.f32.bf16.bf16 "
      "{%0,%1,%2,%3,%4,%5,%6,%7,%8,%9,%10,%11,%12,%13,%14,%15,%16,%17,%18,%19,%20,%21,%22,%23,%24,%25,%26,%27,%28,%29,%30,%31,%32,%33,%34,%35,%36,%37,%38,%39,%40,%41,%42,%43,%44,%45,%46,%47,%48,%49,%50,%51,%52,%53,%54,%55,%56,%57,%58,%59,%60,%61,%62,%63}, "
      "%64, %65, p, 1, 1, 0, 1;\n}\n"
      : "+f"(d[0]), "+f"(d[1]), "+f"(d[2]), "+f"(d[3]), "+f"(d[4]), "+f"(d[5]), "+f"(d[6]), "+f"(d[7]),
        "+f"(d[8]), "+f"(d[9]), "+f"(d[10]), "+f"(d[11]), "+f"(d[12]), "+f"(d[13]), "+f"(d[14]), "+f"(d[15]),
        "+f"(d[16]), "+f"(d[17]), "+f"(d[18]), "+f"(d[19]), "+f"(d[20]), "+f"(d[21]), "+f"(d[22]), "+f"(d[23]),
        "+f"(d[24]), "+f"(d[25]), "+f"(d[26]), "+f"(d[27]), "+f"(d[28]), "+f"(d[29]), "+f"(d[30]), "+f"(d[31]),
        "+f"(d[32]), "+f"(d[33]), "+f"(d[34]), "+f"(d[35]), "+f"(d[36]), "+f"(d[37]), "+f"(d[38]), "+f"(d[39]),
        "+f"(d[40]), "+f"(d[41]), "+f"(d[42]), "+f"(d[43]), "+f"(d[44]), "+f"(d[45]), "+f"(d[46]), "+f"(d[47]),
        "+f"(d[48]), "+f"(d[49]), "+f"(d[50]), "+f"(d[51]), "+f"(d[52]), "+f"(d[53]), "+f"(d[54]), "+f"(d[55]),
        "+f"(d[56]), "+f"(d[57]), "+f"(d[58]), "+f"(d[59]), "+f"(d[60]), "+f"(d[61]), "+f"(d[62]), "+f"(d[63])
      : "l"(da), "l"(db), "r"(sc));
}

__device__ __forceinline__ void wgmma_ss_n40(float (&d)[20], uint64_t da, uint64_t db, int sc) {
  asm volatile("{\n.reg .pred p;\nsetp.ne.b32 p, %22, 0;\n"
      "wgmma.mma_async.sync.aligned.m64n40k16.f32.bf16.bf16 "
      "{%0,%1,%2,%3,%4,%5,%6,%7,%8,%9,%10,%11,%12,%13,%14,%15,%16,%17,%18,%19}, "
      "%20, %21, p, 1, 1, 1, 1;\n}\n"
      : "+f"(d[0]), "+f"(d[1]), "+f"(d[2]), "+f"(d[3]), "+f"(d[4]), "+f"(d[5]), "+f"(d[6]), "+f"(d[7]),
        "+f"(d[8]), "+f"(d[9]), "+f"(d[10]), "+f"(d[11]), "+f"(d[12]), "+f"(d[13]), "+f"(d[14]), "+f"(d[15]),
        "+f"(d[16]), "+f"(d[17]), "+f"(d[18]), "+f"(d[19])
      : "l"(da), "l"(db), "r"(sc));
}

__device__ __forceinline__ void wgmma_rs_n8(float (&d)[4], const uint4& a, uint64_t db, int sc) {
  asm volatile("{\n.reg .pred p;\nsetp.ne.b32 p, %9, 0;\n"
      "wgmma.mma_async.sync.aligned.m64n8k16.f32.bf16.bf16 "
      "{%0,%1,%2,%3}, "
      "{%4,%5,%6,%7}, %8, p, 1, 1, 1;\n}\n"
      : "+f"(d[0]), "+f"(d[1]), "+f"(d[2]), "+f"(d[3])
      : "r"(a.x), "r"(a.y), "r"(a.z), "r"(a.w), "l"(db), "r"(sc));
}

__device__ __forceinline__ void wgmma_rs_n16(float (&d)[8], const uint4& a, uint64_t db, int sc) {
  asm volatile("{\n.reg .pred p;\nsetp.ne.b32 p, %13, 0;\n"
      "wgmma.mma_async.sync.aligned.m64n16k16.f32.bf16.bf16 "
      "{%0,%1,%2,%3,%4,%5,%6,%7}, "
      "{%8,%9,%10,%11}, %12, p, 1, 1, 1;\n}\n"
      : "+f"(d[0]), "+f"(d[1]), "+f"(d[2]), "+f"(d[3]), "+f"(d[4]), "+f"(d[5]), "+f"(d[6]), "+f"(d[7])
      : "r"(a.x), "r"(a.y), "r"(a.z), "r"(a.w), "l"(db), "r"(sc));
}

__device__ __forceinline__ void wgmma_rs_n24(float (&d)[12], const uint4& a, uint64_t db, int sc) {
  asm volatile("{\n.reg .pred p;\nsetp.ne.b32 p, %17, 0;\n"
      "wgmma.mma_async.sync.aligned.m64n24k16.f32.bf16.bf16 "
      "{%0,%1,%2,%3,%4,%5,%6,%7,%8,%9,%10,%11}, "
      "{%12,%13,%14,%15}, %16, p, 1, 1, 1;\n}\n"
      : "+f"(d[0]), "+f"(d[1]), "+f"(d[2]), "+f"(d[3]), "+f"(d[4]), "+f"(d[5]), "+f"(d[6]), "+f"(d[7]),
        "+f"(d[8]), "+f"(d[9]), "+f"(d[10]), "+f"(d[11])
      : "r"(a.x), "r"(a.y), "r"(a.z), "r"(a.w), "l"(db), "r"(sc));
}

struct Params {
  const __nv_bfloat16 *logA, *Aim, *Cre, *Cim, *logdt, *Dskip, *x, *wphi, *wo;
  __nv_bfloat16* out;
  uint4* xs;
  long long* ts;
};

__device__ __forceinline__ uint4 tr_row(const uint4 (&v)[8], int i) {
  uint32_t o[4];
#pragma unroll
  for (int m = 0; m < 4; m++) {
    const uint4 &ra = v[2 * m], &rb = v[2 * m + 1];
    const int k = i >> 1;
    const uint32_t xa = k == 0 ? ra.x : k == 1 ? ra.y : k == 2 ? ra.z : ra.w;
    const uint32_t xb = k == 0 ? rb.x : k == 1 ? rb.y : k == 2 ? rb.z : rb.w;
    o[m] = __byte_perm(xa, xb, (i & 1) ? 0x7632 : 0x5410);
  }
  return make_uint4(o[0], o[1], o[2], o[3]);
}

struct cpx { float r, i; };
__device__ __forceinline__ cpx csq(cpx a) { return {a.r * a.r - a.i * a.i, 2.f * (a.r * a.i)}; }
__device__ __forceinline__ cpx polar(float e, float t) {
  const float m = ex2(e);
  return {m * __cosf(t), m * __sinf(t)};
}

struct KgenRaw { uint32_t la, ai, cr, ci, ldt; };
__device__ __forceinline__ KgenRaw kgen_load(const Params& P, int d, int unit, int lane, int on) {
  const int o = d * 64 + unit * 32 + lane;
  KgenRaw r = {0, 0, 0, 0, 0};
  asm volatile("{\n.reg .pred p;\nsetp.ne.b32 p, %10, 0;\n@p ld.global.nc.u32 %0, [%5];\n@p ld.global.nc.u32 %1, [%6];\n"
               "@p ld.global.nc.u32 %2, [%7];\n@p ld.global.nc.u32 %3, [%8];\n@p ld.global.nc.u16 %4, [%9];\n}\n"
               : "+r"(r.la), "+r"(r.ai), "+r"(r.cr), "+r"(r.ci), "+r"(r.ldt)
               : "l"((const uint32_t*)P.logA + o), "l"((const uint32_t*)P.Aim + o), "l"((const uint32_t*)P.Cre + o),
                 "l"((const uint32_t*)P.Cim + o), "l"(P.logdt + d), "r"(on));
  return r;
}
struct hc { __half2 r, i; };
struct cpx2 { cpx a, b; };
__device__ __forceinline__ cpx2 csq2(const cpx2& v) { return {csq(v.a), csq(v.b)}; }
__device__ __forceinline__ hc toh(const cpx2& v) { return {__floats2half2_rn(v.a.r, v.b.r), __floats2half2_rn(v.a.i, v.b.i)}; }
__device__ __forceinline__ hc hmul(const hc& z, const hc& w) {
  return {__hfma2(z.r, w.r, __hneg2(__hmul2(z.i, w.i))), __hfma2(z.r, w.i, __hmul2(z.i, w.r))};
}
__device__ __forceinline__ hc hmulc(const hc& z, const hc& w) {
  return {__hfma2(z.r, w.r, __hmul2(z.i, w.i)), __hfma2(z.i, w.r, __hneg2(__hmul2(z.r, w.i)))};
}
__device__ __forceinline__ uint32_t hu(__half2 v) { return *(const uint32_t*)&v; }
__device__ __forceinline__ __half2 uh(uint32_t v) { return *(const __half2*)&v; }

struct KgenAddr { uint32_t sa, lb, lm[4]; };
__device__ __forceinline__ KgenAddr kgen_addr(int lane, uint32_t buf) {
  KgenAddr a;
  a.sa = buf + (lane & 7) * 128 + ((((lane >> 3) ^ lane) & 7) << 4);
  const int q = lane >> 4;
  const uint32_t b = buf + ((lane >> 3) & 1) * 1024 + q * 128;
  a.lb = b + (((lane ^ q) & 7) << 4);
  a.lm[0] = b + (q << 4);
  a.lm[1] = b + ((1 ^ q) << 4);
  a.lm[2] = b + (((2 + (lane & 1)) ^ q) << 4);
  a.lm[3] = b + (((4 + (lane & 3)) ^ q) << 4);
  asm volatile("" : "+r"(a.sa), "+r"(a.lb), "+r"(a.lm[0]), "+r"(a.lm[1]), "+r"(a.lm[2]), "+r"(a.lm[3]));
  return a;
}
__device__ __forceinline__ void kgen_unit(const KgenRaw& r, const KgenAddr& ad, uint32_t zero, float (&k)[5][4], float& k2048, float& sc) {
  const float dt = bf_round(expf(bf_lo(r.ldt)));
  const uint32_t ar = pack_bf(ex2(bf_lo(r.la) * 1.4426950408889634f), ex2(bf_hi(r.la) * 1.4426950408889634f));
  const float ca = dt * -1.4426950408889634f, a0 = bf_lo(ar) * ca, a1 = bf_hi(ar) * ca;
  const float f0 = bf_lo(r.ai) * dt, f1 = bf_hi(r.ai) * dt;
  const float r0 = f0 * 20.21267777267071f, r1 = f1 * 20.21267777267071f;
  const uint32_t cm = __vmaxu2(r.cr & 0x7fff7fffu, r.ci & 0x7fff7fffu);
  const uint32_t ex = min(max(__reduce_max_sync(0xffffffffu, max(cm >> 16, cm & 0xffffu)) >> 7, 1u), 253u);
  const float cs = uf((254u - ex) << 23);
  sc = 2.f * dt * uf(ex << 23);
  const cpx2 C = {{bf_lo(r.cr) * cs, bf_lo(r.ci) * -cs}, {bf_hi(r.cr) * cs, bf_hi(r.ci) * -cs}};
  auto put = [&](const hc (&v)[8]) {
    stsm4(ad.sa, hu(v[0].r), hu(v[1].r), hu(v[2].r), hu(v[3].r));
    stsm4(ad.sa + 1024, hu(v[0].i), hu(v[1].i), hu(v[2].i), hu(v[3].i));
    stsm4(ad.sa ^ 64, hu(v[4].r), hu(v[5].r), hu(v[6].r), hu(v[7].r));
    stsm4((ad.sa ^ 64) + 1024, hu(v[4].i), hu(v[5].i), hu(v[6].i), hu(v[7].i));
    __syncwarp();
  };
  auto get = [&](uint32_t (&o)[4][4], uint32_t a) {
#pragma unroll
    for (int i = 0; i < 4; i++) ldsm4(o[i], (a ^ (i << 5)) + i * 256);
  };
  auto at = [](const uint32_t (&o)[4][4], int s) { return hc{uh(o[s >> 1][2 * (s & 1)]), uh(o[s >> 1][2 * (s & 1) + 1])}; };
  uint32_t A[8][4];
  auto tile = [&](int j, const uint32_t (&B)[4][4]) {
    k[j][0] = k[j][1] = k[j][2] = k[j][3] = 0.f;
#pragma unroll
    for (int s = 0; s < 8; s++) mma_h(k[j], A[s], B[s >> 1][2 * (s & 1)], B[s >> 1][2 * (s & 1) + 1]);
  };
  const cpx2 w1 = {polar(a0, f0), polar(a1, f1)};
  const cpx2 w127 = {polar(a0 * 127.f, (r0 - rintf(r0)) * 6.283185307179586f), polar(a1 * 127.f, (r1 - rintf(r1)) * 6.283185307179586f)};
  const cpx2 w2 = csq2(w1), w4 = csq2(w2);
  uint32_t T0[4][4], X[4][4], M[3][4][4];
  {
    hc t[8];
    t[0] = {uh(0x3C003C00u), uh(0u)}; t[1] = toh(w1); t[2] = toh(w2); t[4] = toh(w4);
    t[3] = hmul(t[1], t[2]); t[5] = hmul(t[1], t[4]); t[6] = hmul(t[2], t[4]); t[7] = hmul(t[3], t[4]);
    put(t); get(T0, ad.lb);
  }
  const cpx2 w8 = csq2(w4), w16 = csq2(w8), w32 = csq2(w16), w64 = csq2(w32);
  {
    const hc m8 = toh(w8), m16 = toh(w16), m32 = toh(w32);
    hc a[8];
    a[0] = toh(C); a[1] = hmulc(a[0], m8);
    a[2] = hmulc(a[0], m16); a[3] = hmulc(a[1], m16);
#pragma unroll
    for (int i = 0; i < 4; i++) a[4 + i] = hmulc(a[i], m32);
    put(a); get(X, ad.lb);
  }
    const cpx2 w128 = {{w127.a.r * w1.a.r - w127.a.i * w1.a.i, w127.a.r * w1.a.i + w127.a.i * w1.a.r},
                     {w127.b.r * w1.b.r - w127.b.i * w1.b.i, w127.b.r * w1.b.i + w127.b.i * w1.b.r}};
  const cpx2 w256 = csq2(w128), w512 = csq2(w256);
  const hc m128 = toh(w128), m256 = toh(w256), m512 = toh(w512);
  {
    const hc m254 = toh(csq2(w127)), m127 = toh(w127);
    hc m[8];
    m[0] = toh(w64); m[1] = m128; m[2] = m256; m[3] = hmul(m127, m256);
    m[4] = m512; m[5] = hmul(m127, m512); m[6] = hmul(m[4], m254); m[7] = hmul(m[5], m254);
    put(m);
    get(M[0], ad.lm[0]);
#pragma unroll
    for (int s = 0; s < 8; s++) {
      const hc z = at(X, s), y = hmulc(z, at(M[0], s));
      A[s][0] = hu(z.r) + zero; A[s][1] = hu(y.r); A[s][2] = hu(z.i) + zero; A[s][3] = hu(y.i);
    }
#pragma unroll
    for (int i = 0; i < 3; i++) get(M[i], ad.lm[i + 1]);
  }
  tile(0, T0);
  const cpx2 w1024 = csq2(w512), we = csq2(w1024);
  {
    hc t[8];
    t[0] = toh(w1024); t[1] = hmul(t[0], m128);
    t[2] = hmul(t[0], m256); t[3] = hmul(t[1], m256);
#pragma unroll
    for (int i = 0; i < 4; i++) t[4 + i] = hmul(t[i], m512);
    put(t); get(X, ad.lb);
  }
  k2048 = (C.a.r * we.a.r + C.a.i * we.a.i + C.b.r * we.b.r + C.b.i * we.b.i) * sc;
#pragma unroll
  for (int j = 1; j < 5; j++) k[j][0] = k[j][1] = k[j][2] = k[j][3] = 0.f;
#pragma unroll
  for (int s = 0; s < 8; s++) {
#pragma unroll
    for (int j = 0; j < 3; j++) {
      const hc y = hmul(at(T0, s), at(M[j], s));
      mma_h(k[1 + j], A[s], hu(y.r), hu(y.i));
    }
    mma_h(k[4], A[s], X[s >> 1][2 * (s & 1)], X[s >> 1][2 * (s & 1) + 1]);
  }
}

__device__ __forceinline__ void build_tables(uint32_t tb, int lane, float (&k)[5][4], float k2048) {
  const int g = lane >> 2, c = lane & 3;
  const uint32_t kc = tb + T_KC + 16;
  {
    const uint32_t a0 = kc + 16 * g + 4 * c, a2 = kc + 2 * (256 + 4 * g + c);
    const uint32_t a3 = kc + 2 * (384 + 2 * g + 64 * (c & 1) + (c >> 1)), a4 = kc + 2 * (512 + g + 32 * c);
#pragma unroll
    for (int r = 0; r < 2; r++) {
      sts32(a0 + 128 * r, pack_bf(k[0][2 * r], k[0][2 * r + 1]));
      sts32(a0 + 128 * r + 256, pack_bf(k[1][2 * r], k[1][2 * r + 1]));
      const uint32_t w2 = pack_bf(k[2][2 * r], k[2][2 * r + 1]);
      const uint32_t w3 = pack_bf(k[3][2 * r], k[3][2 * r + 1]);
      const uint32_t w4 = pack_bf(k[4][2 * r], k[4][2 * r + 1]);
      sts16(a2 + 64 * r, w2); sts16(a2 + 64 * r + 128, w2 >> 16);
      sts16(a3 + 32 * r, w3); sts16(a3 + 32 * r + 64, w3 >> 16);
      sts16(a4 + 16 * r, w4); sts16(a4 + 16 * r + 32, w4 >> 16);
    }
  }
  if (lane == 0) { sts16(kc + 2 * 640, pack_bf(k2048, 0.f)); sts32(kc - 4, 0); }
  __syncwarp();
  const uint32_t td = tb + T_D + 32;
#pragma unroll
  for (int hf = 0; hf < 2; hf++) {
    const uint2 v = lds64(kc + 256 * hf + 8 * lane);
    const uint32_t pv = lds32(kc + 256 * hf + 8 * lane - 4);
    sts128(td + 512 * hf + 16 * lane, __byte_perm(v.x, pv, 0x7610), __byte_perm(v.x, v.x, 0x1032), __byte_perm(v.y, v.x, 0x7610),
           __byte_perm(v.y, v.y, 0x1032));
  }
#pragma unroll
  for (int hf = 0; hf < 2; hf++) {
    const uint32_t v = lds32(kc + 512 + 128 * hf + 4 * lane), nx = lds32(kc + 516 + 128 * hf + 4 * lane);
    uint32_t w0 = __byte_perm(v, v, 0x1010);
    const uint32_t w1 = w0;
    if (hf == 0) { const uint32_t pv = lds32(kc + 508); if (lane == 0) w0 = __byte_perm(v, pv, 0x7610); }
    sts128(td + 1024 + 512 * hf + 16 * lane, w0, w1, __byte_perm(v, v, 0x1032), __byte_perm(nx, v, 0x7610));
  }
  {
    const uint32_t kk = lds16(kc + 2 * 384);
    const uint32_t w = lane < 3 ? (kk | (kk << 16)) : (lane == 3 ? (kk << 16) : 0u);
    if (lane < 24) sts32(td + 4 * (lane < 16 ? 512 + lane : lane - 24), w);
    const uint32_t lo_ = lds16(kc + 2 * 511), le_ = lds16(kc + 2 * 512);
    const uint32_t ja = tb + T_5 + (lane < 16 ? 4 * lane : 256 + 4 * lane);
    sts32(ja, lane == 16 ? (le_ << 16) : 0u);
    sts32(ja + 384, lane == 16 ? (lo_ << 16) : 0u);
    sts32(tb + (lane < 16 ? T_7 : T_9 - 64) + 4 * lane, 0u);
  }
#pragma unroll
  for (int s = 0; s < 2; s++) {
    const uint32_t b = kc + 2 * (s ? 512 : 384) + 8 * lane;
    const uint2 v = lds64(b);
    uint32_t em = lds16(b - 2), e0 = v.x;
    const uint32_t e4 = lds16(b + 8);
    if (lane == 0) { em = 0; e0 = 0; }
    sts64(tb + (s ? T_7 : T_3) + 64 + 8 * lane, __byte_perm(v.x, em, 0x5432), __byte_perm(v.y, v.x, 0x7632));
    sts64(tb + (s ? T_9 : T_5) + 64 + 8 * lane, __byte_perm(v.y, e0, 0x5410), __byte_perm(e4, v.y, 0x5410));
  }
  __syncwarp();
}

__device__ __forceinline__ uint32_t box2w(int lo, int n, int o) {
  return ((unsigned)(o - lo) < (unsigned)n ? 0x3F80u : 0u) | ((unsigned)(o + 1 - lo) < (unsigned)n ? 0x3F800000u : 0u);
}

__device__ __forceinline__ void conv_channel(uint32_t ub, uint32_t tb, int lane, uint4* ydst) {
  const int g = lane >> 2, c = lane & 3, x = g - 2 * c;
  const int mi = lane >> 3;
  const uint32_t qa = ub + U_PAD + 16 * (lane & 7) + ((mi == 0 || mi == 3) ? U_ODD : 0) - (mi == 0 ? 16 : 0);
  const uint32_t hb = ub + U_PAD + (mi & 1) * U_ODD + 16 * ((lane >> 4) + (lane & 7)) - 16;
  const uint32_t kv = lds16(tb + T_KC + 16 + 2 * 512);
  const int oh = c < 2 ? 8 + 2 * c : 2 * c - 8, og = c < 3 ? 2 * c : -10;
  uint32_t bx[4] = {box2w(g - 4, 9, 2 * c), box2w(g - 3, 7, 2 * c), box2w(g - 4, 9, oh), box2w(g - 3, 7, oh)};
  uint32_t by[4] = {box2w(g - 10, 5, 2 * c - 8), box2w(g - 5, 3, 2 * c - 8), box2w(g - 10, 5, og), box2w(g - 5, 3, og)};
  uint32_t lb0 = ((unsigned)(x + 5) < 2u ? kv : 0u) | ((unsigned)(x + 4) < 2u ? kv << 16 : 0u);
  uint32_t lb1 = ((unsigned)(x - 3) < 2u ? kv : 0u) | ((unsigned)(x - 4) < 2u ? kv << 16 : 0u);
  const int q0 = g - 1, q1 = c < 3 ? g : g - 2;
  uint32_t y0a = ub + U_PAD + (q0 & 1) * U_ODD + 16 * (q0 >> 1) + 4 * c;
  uint32_t y1a = ub + U_PAD + (q1 & 1) * U_ODD + 16 * (q1 >> 1) + 4 * c;
#pragma unroll
  for (int i = 0; i < 4; i++) asm volatile("" : "+r"(bx[i]), "+r"(by[i]));
  asm volatile("" : "+r"(lb0), "+r"(lb1), "+r"(y0a), "+r"(y1a));
  mbar_wait(BAR(MB_UFULL));
  mbar_spin(BAR(MB_EMPTY + 15));
  TS(36);
  float acc[16][4];
  {
    uint32_t z09[8], z07[8], zm9[8], zm7[8];
#pragma unroll
    for (int i = 0; i < 8; i++) {
      uint32_t h[4];
      ldsm4(h, hb + 128 * i);
      float y0, y1, y2, y3, w0, w1, w2, w3;
      mma0(y0, y1, y2, y3, bx[0], bx[1], bx[2], bx[3], h[2], c < 2 ? h[3] : h[1]);
      mma0(w0, w1, w2, w3, bx[0], bx[1], bx[2], bx[3], h[1], c < 2 ? h[2] : h[0]);
      z09[i] = pack_bf(y0, y1); z07[i] = pack_bf(y2, y3);
      zm9[i] = pack_bf(w0, w1); zm7[i] = pack_bf(w2, w3);
    }
  uint32_t f3[3][4][4];
  {
    const uint32_t fa = tb + T_7 + 4 * (16 + x);
#pragma unroll
    for (int tt = 0; tt < 3; tt++)
#pragma unroll
      for (int D = 0; D < 4; D++) {
        const uint32_t a = fa + (tt == 0 ? 316 : (tt == 1 ? 320 : 0)) + 64 * D;
        f3[tt][D][0] = lds32(a); f3[tt][D][1] = lds32(a + 32); f3[tt][D][2] = lds32(a - 32); f3[tt][D][3] = lds32(a);
      }
  }
    SPLIT();
    nb_sync(NB_GATE, 256);
    SPLIT();
    float a[4][2][4];
#pragma unroll
    for (int kap = 0; kap < 4; kap++)
#pragma unroll
      for (int sg = 0; sg < 2; sg++)
#pragma unroll
        for (int bk = 3; bk >= kap; bk--) {
          const uint32_t(&q0_)[4] = f3[sg ? 2 : 0][bk - kap];
          const uint32_t(&q1_)[4] = f3[sg ? 2 : 1][bk - kap];
          float(&a0)[4] = a[bk][0];
          float(&a1)[4] = a[bk][1];
          if (sg == 0 && kap == 0) {
            mma0(a0[0], a0[1], a0[2], a0[3], q0_[0], q0_[1], q0_[2], q0_[3], z09[0], z09[1]);
            mma0(a1[0], a1[1], a1[2], a1[3], q1_[0], q1_[1], q1_[2], q1_[3], zm9[0], zm9[1]);
          } else {
            mma(a0[0], a0[1], a0[2], a0[3], q0_[0], q0_[1], q0_[2], q0_[3], sg ? zm7[2 * kap] : z09[2 * kap], sg ? zm7[2 * kap + 1] : z09[2 * kap + 1]);
            mma(a1[0], a1[1], a1[2], a1[3], q1_[0], q1_[1], q1_[2], q1_[3], sg ? z07[2 * kap] : zm9[2 * kap], sg ? z07[2 * kap + 1] : zm9[2 * kap + 1]);
          }
        }
    SPLIT();
#pragma unroll
    for (int i = 0; i < 8; i++) {
      uint32_t h[4];
      ldsm4(h, qa + 128 * i);
      const float ci[4] = {a[i >> 1][0][2 * (i & 1)], a[i >> 1][0][2 * (i & 1) + 1], a[i >> 1][1][2 * (i & 1)], a[i >> 1][1][2 * (i & 1) + 1]};
      mmac(acc[8 + i], h[0], h[1], h[2], h[3], lb0, lb1, ci);
    }
  }
  TS(44);
  {
    uint2 a5[10], a3[10];
    const uint32_t aa = tb + T_5 + 4 * (8 + 2 * g - 2 * c);
#pragma unroll
    for (int m = 0; m < 10; m++) { a5[m] = lds64(aa + 32 * m); a3[m] = lds64(aa + 384 + 32 * m); }
    uint32_t x5[12][2], x3[12][2];
    auto ygen = [&](int kap) {
#pragma unroll
      for (int hh = 0; hh < 2; hh++) {
        float y0, y1, y2, y3;
        mma0(y0, y1, y2, y3, by[0], by[1], by[2], by[3], lds32(y0a + 128 * kap + 64 * hh), lds32(y1a + 128 * kap + 64 * hh));
        x5[kap][hh] = pack_bf(y0, y1);
        x3[kap][hh] = pack_bf(y2, y3);
      }
    };
    ygen(11); ygen(10); ygen(9); ygen(8);
#pragma unroll
    for (int kap = 11; kap >= 0; kap--) {
      if (kap >= 4) ygen(kap - 4);
#pragma unroll
      for (int sg = 0; sg < 2; sg++)
#pragma unroll
        for (int i = 4; i >= 0; i--) {
          const int be = kap + 4 + i;
          if (be <= 15) {
            const uint2 &hi = sg ? a3[2 * i + 1] : a5[2 * i + 1], &lo = sg ? a3[2 * i] : a5[2 * i];
            const uint32_t b0 = sg ? x3[kap][0] : x5[kap][0], b1 = sg ? x3[kap][1] : x5[kap][1];
            if (be < 8 && i == 0 && sg == 0) mma0(acc[be][0], acc[be][1], acc[be][2], acc[be][3], hi.x, hi.y, lo.x, lo.y, b0, b1);
            else mma(acc[be][0], acc[be][1], acc[be][2], acc[be][3], hi.x, hi.y, lo.x, lo.y, b0, b1);
          }
        }
    }
  }
  TS(45);
  {
    const uint32_t st = tb + T_ST + lane * 8;
#pragma unroll
    for (int be = 4; be < 12; be++) sts64(st + 256 * be, pack_bf(acc[be][0], acc[be][1]), pack_bf(acc[be][2], acc[be][3]));
    SPLIT();
    uint32_t F[66], qd[8][4];
    const uint32_t fa = tb + T_D + 32 + 4 * x;
#pragma unroll
    for (int i = 0; i < 32; i++) {
      const int s = 120 - (i >> 2) - 8 * (i & 3);
      uint32_t(&q)[4] = qd[i & 7];
      ldsm4(q, qa + 16 * s);
      const int m = 16 * (i & 3) + 2 * (i >> 2);
      F[m] = lds32(fa + 32 * m); F[m + 1] = lds32(fa + 32 * m + 32);
#pragma unroll
      for (int be = 15; be >= 12; be--) {
        const int de = 8 * be - s;
        float(&a)[4] = (be >= 14 && !(i & 1)) ? acc[be - 4] : acc[be];
        if (de >= 0 && be >= 14 && i == 2 * (15 - be)) mma0(a[0], a[1], a[2], a[3], q[0], q[1], q[2], q[3], F[2 * de + 1], F[2 * de]);
        else if (de >= 0) mma(a[0], a[1], a[2], a[3], q[0], q[1], q[2], q[3], F[2 * de + 1], F[2 * de]);
      }
    }
#pragma unroll
    for (int i = 0; i < 8; i++) acc[14 + (i >> 2)][i & 3] += acc[10 + (i >> 2)][i & 3];
    F[64] = lds32(fa + 32 * 64); F[65] = lds32(fa + 32 * 65);
#pragma unroll
    for (int i = 0; i < 6; i++) ldsm4(qd[i], qa + 128 * 11 - 16 * i);
    uint2 sv = lds64(st + 256 * 11);
    float ci[4] = {bf_lo(sv.x), bf_hi(sv.x), bf_lo(sv.y), bf_hi(sv.y)};
    float T[5][4];
#pragma unroll
    for (int i = 0; i < 16; i++) T[i >> 2][i & 3] = acc[12 + (i >> 2)][i & 3];
    nb_sync(NB_YZ, 160);
    TS(46);
    uint32_t held[2];
#pragma unroll
    for (int be = 11; be >= 0; be--) {
      if (be & 1) SPLITN(be);
      const uint32_t qp = qa + 128 * be;
#pragma unroll
      for (int k = 4; k >= 1; k--) mmac(T[k], qd[0][0], qd[0][1], qd[0][2], qd[0][3], F[16 * k + 1], F[16 * k], T[k - 1]);
      if (be >= 4) mmac(T[0], qd[0][0], qd[0][1], qd[0][2], qd[0][3], F[1], F[0], ci);
      else mma0(T[0][0], T[0][1], T[0][2], T[0][3], qd[0][0], qd[0][1], qd[0][2], qd[0][3], F[1], F[0]);
      ldsm4(qd[6], qp - 16 * 6);
      ldsm4(qd[7], qp - 16 * 7);
      if (be > 4) sv = lds64(st + 256 * (be - 1));
#pragma unroll
      for (int i = 1; i < 8; i++) {
#pragma unroll
        for (int k = 3; k >= 0; k--)
          mma(T[k][0], T[k][1], T[k][2], T[k][3], qd[i][0], qd[i][1], qd[i][2], qd[i][3], F[16 * k + 2 * i + 1], F[16 * k + 2 * i]);
        if (i < 7 && be > 0) ldsm4(qd[i - 1], qp - 128 - 16 * (i - 1));
        if (i == 2) {
          const uint32_t w0 = pack_bf(T[4][0], T[4][1]), w1 = pack_bf(T[4][2], T[4][3]);
          if (be & 1) { held[0] = w0; held[1] = w1; }
          else st_x(ydst + (be + 4) * 16, nz(w0), w1, held[0], held[1]);
          if ((be & 3) == 3 && be < 11) nb_arrive(NB_Y + 2 + (be >> 2), 160);
        }
        if (i == 4 && be > 4) { ci[0] = bf_lo(sv.x); ci[1] = bf_hi(sv.x); ci[2] = bf_lo(sv.y); ci[3] = bf_hi(sv.y); }
      }
    }
    nb_arrive(NB_Y + 1, 160);
#pragma unroll
    for (int B = 1; B >= 0; B--)
      st_x(ydst + B * 32, nz(pack_bf(T[2 * B][0], T[2 * B][1])), pack_bf(T[2 * B][2], T[2 * B][3]),
           pack_bf(T[2 * B + 1][0], T[2 * B + 1][1]), pack_bf(T[2 * B + 1][2], T[2 * B + 1][3]));
  }
}

__device__ __forceinline__ void dual_exp(const uint32_t* w, uint32_t* e) {
  const float L = 1.44268798828125f;
  uint32_t mx = bmax2(bmax2(w[0], w[1]), bmax2(w[2], w[3]));
  uint32_t mn = bmin2(bmin2(w[0], w[1]), bmin2(w[2], w[3]));
  mx = bmax2(mx, __shfl_xor_sync(0xffffffffu, mx, 1));
  mn = bmin2(mn, __shfl_xor_sync(0xffffffffu, mn, 1));
  mx = bmax2(mx, __shfl_xor_sync(0xffffffffu, mx, 2));
  mn = bmin2(mn, __shfl_xor_sync(0xffffffffu, mn, 2));
  const float mx0 = bf_lo(mx) * -L, mx1 = bf_hi(mx) * -L, mn0 = bf_lo(mn) * L, mn1 = bf_hi(mn) * L;
#pragma unroll
  for (int i = 0; i < 2; i++) {
    const float a0 = bf_lo(w[2 * i]), a1 = bf_hi(w[2 * i]), b0 = bf_lo(w[2 * i + 1]), b1 = bf_hi(w[2 * i + 1]);
    e[2 * i] = pack_bf(ex2(fmaf(a0, L, mx0)), ex2(fmaf(b0, L, mx0)));
    e[2 * i + 1] = pack_bf(ex2(fmaf(a1, L, mx1)), ex2(fmaf(b1, L, mx1)));
    e[4 + 2 * i] = pack_bf(ex2(fmaf(a0, -L, mn0)), ex2(fmaf(b0, -L, mn0)));
    e[5 + 2 * i] = pack_bf(ex2(fmaf(a1, -L, mn1)), ex2(fmaf(b1, -L, mn1)));
  }
}
__device__ __forceinline__ void normalise(uint32_t* e, const float (&s)[4]) {
  const uint32_t r = pack_bf(rcp(s[0]), rcp(s[2]));
  const __nv_bfloat162 rr = *(const __nv_bfloat162*)&r;
#pragma unroll
  for (int i = 0; i < 4; i++) {
    const __nv_bfloat162 v = __hmul2(*(const __nv_bfloat162*)&e[i], (i & 1) ? __high2bfloat162(rr) : __low2bfloat162(rr));
    e[i] = *(const uint32_t*)&v;
  }
}
__host__ __device__ constexpr uint64_t qdesc(uint32_t addr) { return mkdesc(addr, 128, 256, 0); }

__global__ void __launch_bounds__(NTHREADS, 1)
fused_kernel(const Params P, const __grid_constant__ CUtensorMap mx, const __grid_constant__ CUtensorMap mw,
             const __grid_constant__ CUtensorMap mo, const __grid_constant__ CUtensorMap mu,
             const __grid_constant__ CUtensorMap mout) {
  constexpr uint32_t sb = SB;
  const int tid = threadIdx.x, lane = tid & 31;
  const int warp = __shfl_sync(0xffffffffu, tid >> 5, 0);
  const int b = blockIdx.x, oct = b >> 3, i8 = b & 7;
  const int rt = (((oct & 4) ? ~oct : oct) & 3) * 2 + (i8 >> 2);
  const int hp = (oct >> 2) * 4 + (i8 & 3);

  const int wg = warp >> 2, w = warp & 3;
  const int d = b * 4 + ((tid >> 5) & 3);
  const KgenRaw raw = kgen_load(P, d, (tid >> 7) & 1, lane, (tid + 128) & 256);
  const uint32_t tb = sb + OFF_T + w * T_CH;
  if (warp >= 12) {
    asm volatile("setmaxnreg.dec.sync.aligned.u32 32;");
    if (warp == 12) {
      if (lane == 0) {
#pragma unroll
        for (int i = 0; i < 9; i++) mbar_init(BAR(i), 1);
        asm volatile("fence.mbarrier_init.release.cluster;" ::: "memory");
      }
      __syncwarp();
      if (lane < 9) mbar_expect(BAR(0) + 8 * lane, lane == 0 ? 16384 : 28672);
      __syncwarp();
      nb_arrive(NB_PROD, 384);
#pragma unroll 1
      for (int kb = 0; kb < 8; kb++) {
        if (kb == U_AT) e_tma4d(sb + OFF_STG0, &mu, BAR(MB_URAW), i8 * 64, oct * 2);
        e_tma3d(sb + OFF_W + kb * 12288, &mw, BAR(MB_FULL) + 8 * kb, hp * 32, kb * 64, 0);
        if (kb < 5) e_tma2d(sb + OFF_X + (kb < 2 ? kb + 3 : kb - 2) * 16384, &mx, BAR(MB_FULL) + 8 * kb, kb * 64, rt * 256);
      }
      if (smem_u32(smem_raw) != SB) __trap();
      if (lane == 0) TS1(54);
      nb_sync(NB_GATE + 1, 64);
      e_prefetch(P.x + (size_t)(rt * 256 + 128 + hp * 8) * 512, 8192);
      uint32_t slot = sb + OFF_X + 3 * 16384;
#pragma unroll 1
      for (int n = 0; n < 11; n++) {
        mbar_spin(BAR(MB_EMPTY) + 8 * n);
        const int m = n + 5;
        e_tma2d(slot, &mx, BAR(MB_FULL) + 8 * m, (m & 7) * 64, rt * 256 + (m >> 3) * 128);
        slot = slot == sb + OFF_X + 4 * 16384 ? sb + OFF_X : slot + 16384;
        if (n == 7) {
          e_prefetch(P.wo + (size_t)b * 2048, 4096);
          asm volatile("prefetch.tensormap [%0];" ::"l"(&mo) : "memory");
          asm volatile("prefetch.tensormap [%0];" ::"l"(&mout) : "memory");
        }
      }
#pragma unroll 1
      for (int i = 0; i < 8; i++) {
        mbar_wait(BAR(MB_EMPTY + 10) + 8 * ((0x54332222u >> (4 * i)) & 7));
        const int w0 = (0x54736210u >> (4 * i)) & 7;
        e_tma3d(sb + OFF_W + w0 * 16384, &mo, BAR(MB_WO), 0, w0 * 64, (hp & 3) * 2);
      }
    } else {
      if (warp == 13) {
        if (lane == 0) {
#pragma unroll
          for (int i = 9; i < 40; i++) mbar_init(BAR(i), i < MB_EMPTY ? 1 : 4);
          asm volatile("fence.mbarrier_init.release.cluster;" ::: "memory");
        }
        __syncwarp();
        if (lane < 14 && lane != 9) mbar_expect(BAR(MB_FULL + 8) + 8 * lane, lane == 8 ? 131072 : (lane == 10 ? 8192 : (lane == 13 ? 24576 : 16384)));
        nb_arrive(NB_GATE + 1, 64);
      } else if (warp == 14) {
        asm volatile("prefetch.tensormap [%0];" ::"l"(&mw) : "memory");
        asm volatile("prefetch.tensormap [%0];" ::"l"(&mx) : "memory");
        asm volatile("prefetch.tensormap [%0];" ::"l"(&mu) : "memory");
        e_prefetch(P.x + (size_t)(rt * 256 + hp * 8) * 512, 8192);
      }
      nb_sync(NB_PROD, 384);
      if (warp == 15) {
        const uint4 v0 = __ldg((const uint4*)P.wphi + hp * 64 + lane), v1 = __ldg((const uint4*)P.wphi + hp * 64 + 32 + lane);
        sts128(sb + OFF_PHI + (lane & 1) * 256 + (lane >> 1) * 16, v0.x, v0.y, v0.z, v0.w);
        sts128(sb + OFF_PHI + 512 + (lane & 1) * 256 + (lane >> 1) * 16, v1.x, v1.y, v1.z, v1.w);
        const uint32_t one = (((lane >> 3) ^ (lane >> 4)) & 1) ? 0u : ((lane & 1) ? 0x3F800000u : 0x3F80u);
        const int q = (lane >> 1) & 3;
        sts128(sb + OFF_EYE + lane * 16, q == 0 ? one : 0u, q == 1 ? one : 0u, q == 2 ? one : 0u, q == 3 ? one : 0u);
        sts64(sb + OFF_ONE + lane * 8, 0x3F803F80u, 0x3F803F80u);
        asm volatile("fence.proxy.async.shared::cta;" ::: "memory");
        nb_arrive(NB_KREAD, 160);
      }
      uint32_t* cnt = (uint32_t*)(P.xs + X_CNT) + (warp == 13 ? i8 : (warp == 14 ? 8 + rt : 16 + oct)) * 32;
      const unsigned target = (ld_x32(cnt) & ~15u) + 16;
      if (warp != 14) {
        if (warp == 15) mbar_wait(BAR(MB_EMPTY + ZERO_STEP));
        uint4* pz = P.xs + (warp == 13 ? X_PART + (hp * 8 + rt) * 144 : X_Y + b * 1024) + lane;
#pragma unroll 1
        for (int i = (warp == 13 ? 144 : 1024) - lane; i > 0; i -= 32, pz += 32) st_x(pz, 0, 0, 0, 0);
      }
      if (warp == 15) __syncwarp();
      else nb_sync(warp == 13 ? NB_INIT : NB_ODONE, warp == 13 ? 160 : 288);
      if (lane == 0) asm volatile("red.release.gpu.global.add.u32 [%0], %1;" ::"l"(cnt), "r"(warp == 15 ? 2 : 1) : "memory");
      if (lane == 0) TS1(warp == 13 ? 50 : (warp == 14 ? 57 : 53));
      __syncwarp();
      if (warp == 14) nb_arrive(NB_GATE + 1, 160);
      asm volatile("fence.proxy.async.shared::cta;" ::: "memory");
      if (warp == 13) cnt += ((lane & 1 ? b >> 4 : i8 ^ (lane & 4)) - i8) * 32;
#pragma unroll 1
      for (int i = 0; i < SPIN_MAX; i++) {
        unsigned v;
        asm volatile("ld.acquire.gpu.global.u32 %0, [%1];" : "=r"(v) : "l"(cnt) : "memory");
        if (__all_sync(0xffffffffu, (int)(v - target) >= 0)) break;
      }
      if (lane == 0) TS1(warp == 13 ? 51 : (warp == 14 ? 58 : 55));
      if (warp == 15) { nb_arrive(NB_YZ, 160); return; }
      asm volatile("fence.proxy.async.global;" ::: "memory");
      if (warp == 13) {
        mbar_wait(BAR(MB_EMPTY + 11));
        e_expect(BAR(MB_UFULL), 4 * U_CH);
        e_bulk(sb + OFF_U, P.xs + X_UT + b * (U_CH / 4), 4 * U_CH, BAR(MB_UFULL));
      } else {
        const uint4* src = P.xs + X_O + (rt * 4 + (hp >> 2)) * 4096;
        e_bulk(sb + OFF_X + 32768 + 57344, src + 3584, 8192, BAR(MB_O));
        e_bulk(sb + OFF_X + 32768, src, 16384, BAR(MB_O + 1));
        e_bulk(sb + OFF_X + 49152, src + 1024, 16384, BAR(MB_O + 2));
        e_bulk(sb + OFF_STG0, src + 3200, 6144, BAR(MB_O + 3));
        nb_sync(NB_BDONE, 288);
        asm volatile("fence.proxy.async.shared::cta;" ::: "memory");
        e_bulk(sb + OFF_U, src + 2048, 18432, BAR(MB_O + 3));
      }
    }
    return;
  }

  asm volatile("setmaxnreg.inc.sync.aligned.u32 160;");
  const int t = tid & 127;
  const int g = lane >> 2, c = lane & 3;
  const uint32_t kp = ((tb + 127) & ~127u) + (wg & 1) * 2048;
  const KgenAddr kad = kgen_addr(lane, kp);
  if (wg) nb_sync(NB_PROD, 384);
  float k[5][4], k2048, ksc;
  if (wg) {
    kgen_unit(raw, kad, blockIdx.y, k, k2048, ksc);
    TS(40 + wg);
    if ((fu(k[0][0]) & fu(k[1][0]) & fu(k[2][0]) & fu(k[3][0]) & fu(k[4][0])) == 0xffffffffu) sts32(kp, 0);
  }
  if (wg) nb_arrive(0, 384);
  if (wg) {
    if (wg == 1) {
      uint32_t h[10];
#pragma unroll
      for (int j = 0; j < 10; j++) h[j] = hu(__floats2half2_rn(k[j >> 1][2 * (j & 1)], k[j >> 1][2 * (j & 1) + 1]));
      sts128(kp + lane * 16, h[0], h[1], h[2], h[3]);
      sts128(kp + 512 + lane * 16, h[4], h[5], h[6], h[7]);
      sts128(kp + 1024 + lane * 16, h[8], h[9], fu(k2048), fu(ksc));
      nb_arrive(NB_PREP, 256);
    }
  } else {
    nb_sync(NB_KREAD, 160);
    nb_sync(0, 384);
  }
  if (wg == 1) {
    mbar_wait(BAR(MB_URAW));
    TS(48);
    uint4* dst = P.xs + X_UT + (i8 * 64 + g) * (U_CH / 16) + (w & 1) * (U_ODD / 16) + U_PAD / 16 + oct * 8 + (w >> 1) * 4 + c;
    const int ln = ((lane >> 1) & 3) + 4 * (lane & 1);
    uint32_t r[8][4];
#pragma unroll
    for (int i = 0; i < 8; i++) ldsm4t(r[i], sb + OFF_STG0 + w * 4096 + ((lane >> 3) * 8 + ln) * 128 + ((i ^ ln) << 4));
#pragma unroll
    for (int i = 0; i < 8; i++) dst[i * (U_CH / 2)] = make_uint4(r[i][0], r[i][1], r[i][2], r[i][3]);
    nb_arrive(NB_INIT, 160);
    if (lane == 0) mbar_arrive(BAR(MB_AUX));
  }
  {
    if (wg == 2) {
#pragma unroll
      for (int j = 0; j < 5; j++) { k[j][0] *= ksc; k[j][1] *= ksc; k[j][2] *= ksc; k[j][3] *= ksc; }
      const unsigned short dsk = __ldg((const unsigned short*)P.Dskip + d);
      nb_sync(NB_PREP, 256);
      {
        const uint32_t src = kp + 2048 + lane * 16;
        const uint4 v0 = lds128(src), v1 = lds128(src + 512), v2 = lds128(src + 1024);
        const uint32_t h[10] = {v0.x, v0.y, v0.z, v0.w, v1.x, v1.y, v1.z, v1.w, v2.x, v2.y};
#pragma unroll
        for (int j = 0; j < 10; j++) {
          const float2 f = __half22float2(*(const __half2*)&h[j]);
          k[j >> 1][2 * (j & 1)] = fmaf(f.x, uf(v2.w), k[j >> 1][2 * (j & 1)]);
          k[j >> 1][2 * (j & 1) + 1] = fmaf(f.y, uf(v2.w), k[j >> 1][2 * (j & 1) + 1]);
        }
        k2048 += uf(v2.z);
      }
#pragma unroll
      for (int o2 = 16; o2; o2 >>= 1) k2048 += __shfl_xor_sync(0xffffffffu, k2048, o2);
      if (lane == 0) k[0][0] += bf_lo(dsk);
      __syncwarp();
      TS(34);
      build_tables(tb, lane, k, k2048);
      TS(35);
      uint4* const g_y = P.xs + X_Y;
      conv_channel(sb + OFF_U + w * U_CH, tb, lane, g_y + (size_t)d * 256 + lane);
      nb_arrive(NB_BDONE, 288);
      nb_arrive(NB_Y, 160);
      TS(37);
      if (w == 0) TSDUMP(32);
      return;
    }
    if (wg == 1) {
      mbar_wait(BAR(MB_EMPTY + 4));
      mbar_spin(BAR(MB_EMPTY + 6));
    }
    TS(wg * 16 + 1);
  }

  float acc[2][48];
  {
    uint32_t fb = BAR(MB_FULL) + 64 * wg;
    uint32_t da = (uint32_t)mkdesc(sb + OFF_X, 16, 0, 0) + (wg ? 1024 : 3072), db = (uint32_t)mkdesc(sb + OFF_W, 4096, 0, 0);
    constexpr uint64_t ha = mkdesc(0, 0, 1024, 1), hb = mkdesc(0, 0, 512, 2);
    mbar_spin(fb);
    TS(wg * 16 + 2);
#pragma unroll 1
    for (int kb = 0; kb < 8; kb++) {
      WG_FENCE();
#pragma unroll
      for (int k = 0; k < 4; k++) {
        wgmma_ss_n96(acc[0], ha | (da + 2 * k), hb | (db + 64 * k), k ? 1 : kb);
        wgmma_ss_n96(acc[1], ha | (da + 2 * k + 512), hb | (db + 64 * k), k ? 1 : kb);
      }
      WG_COMMIT();
      if (kb < 7) mbar_spin(fb + 8);
      WG_WAIT(1);
      if (kb > 0) e_arrive(fb + 8 * (MB_EMPTY - MB_FULL - 1));
      fb += 8; db += 768;
      da = da == (uint32_t)mkdesc(sb + OFF_X + 65536, 16, 0, 0) ? da - 4096 : da + 1024;
    }
    WG_WAIT(0);
    e_arrive(fb + 8 * (MB_EMPTY - MB_FULL - 1));
    SPLIT();
  }
  TS(wg * 16 + 3);

  constexpr uint32_t stg0 = sb + OFF_STG0, stg1 = sb + OFF_X + 32768;
  uint4* const g_part = P.xs + X_PART;
  uint4* const g_o = P.xs + X_O;
  constexpr uint32_t kvs = stg0;
  auto pack8 = [](const float* a) { return make_uint4(pack_bf(a[0], a[1]), pack_bf(a[2], a[3]), pack_bf(a[4], a[5]), pack_bf(a[6], a[7])); };
  auto stage_k = [&](auto nt, const uint4* af, const uint4* vp, uint32_t sl, uint32_t free_bar) {
    constexpr int NU = 2 * decltype(nt)::value;
    float p[NU][8], rs[2 * NU][4];
    uint32_t ek[8 * NU];
    WG_FENCE();
#pragma unroll
    for (int u = 0; u < NU; u++) wgmma_rs_n16(p[u], af[u], qdesc(sb + OFF_PHI + (u & 1) * 512), 0);
    WG_COMMIT();
    WG_WAIT(0);
#pragma unroll
    for (int u = 0; u < NU; u++) {
      const uint32_t pw[4] = {pack_bf(p[u][0], p[u][2]), pack_bf(p[u][1], p[u][3]), pack_bf(p[u][4], p[u][6]), pack_bf(p[u][5], p[u][7])};
      dual_exp(pw, ek + 8 * u);
    }
    TS(wg * 16 + 12);
    mbar_spin(free_bar);
    WG_FENCE();
#pragma unroll
    for (int i = 0; i < 2 * NU; i++) wgmma_rs_n8(rs[i], make_uint4(ek[4 * i], ek[4 * i + 1], ek[4 * i + 2], ek[4 * i + 3]), qdesc(sb + OFF_ONE), 0);
    WG_COMMIT();
#pragma unroll
    for (int i = 0; i < NU; i++) stsm4(sl + (i >> 1) * 4 * SLAB + 2048 + (i & 1) * 512, vp[i].x, vp[i].y, vp[i].z, vp[i].w);
    if (NU == 4 || lane < 16) sts128(sl + (lane >> 4) * (4 * SLAB - 256) + 3072, 0x3F803F80u, 0x3F803F80u, 0x3F803F80u, 0x3F803F80u);
    WG_WAIT(0);
#pragma unroll
    for (int i = 0; i < 2 * NU; i++) {
      normalise(ek + 4 * i, rs[i]);
      stsm4(sl + (i >> 2) * 4 * SLAB + (i & 3) * 512, ek[4 * i], ek[4 * i + 1], ek[4 * i + 2], ek[4 * i + 3]);
    }
    asm volatile("fence.proxy.async.shared::cta;" ::: "memory");
  };
  auto contract = [&](float (&kc)[20], uint32_t stg, int acc_in) {
    WG_FENCE();
#pragma unroll
    for (int s = 0; s < 8; s++) wgmma_ss_n40(kc, qdesc(stg + s * SLAB), qdesc(stg + s * SLAB + 2048), s ? 1 : acc_in);
    WG_COMMIT();
    WG_WAIT(0);
  };
  uint32_t eq[32];
  {
    uint4 af[4], aq[4], vp[4];
    float kc[20];
#pragma unroll
    for (int u = 0; u < 4; u++) { af[u] = pack8(acc[u >> 1] + 16 + 8 * (u & 1)); vp[u] = pack8(acc[u >> 1] + 32 + 8 * (u & 1)); }
    const uint32_t hand = stg1 + 16384 + 8192 + w * 2048 + lane * 16;
    if (wg) {
      sts128(hand, af[2].x, af[2].y, af[2].z, af[2].w); sts128(hand + 512, af[3].x, af[3].y, af[3].z, af[3].w);
      sts128(hand + 1024, vp[2].x, vp[2].y, vp[2].z, vp[2].w); sts128(hand + 1536, vp[3].x, vp[3].y, vp[3].z, vp[3].w);
      nb_arrive(NB_HAND, 256);
    }
#pragma unroll
    for (int u = 0; u < 4; u++) aq[u] = pack8(acc[u >> 1] + 8 * (u & 1));
    uint4* pp = g_part + (size_t)(hp * 8 + rt) * 144 + t;
#pragma unroll 1
    for (int ps = wg * 2; ps < 3; ps++) {
      uint32_t sl = (ps == 2 ? stg1 : stg0) + (w + ((ps && !wg) ? 4 : 0)) * SLAB + lane * 16;
      asm volatile("" : "+r"(sl));
      stage_k(std::integral_constant<int, 1>(), af, vp, sl, ps == 2 ? BAR(MB_EMPTY + 15) : BAR(MB_AUX));
      if (ps == 0) {
        af[0] = af[2]; af[1] = af[3]; vp[0] = vp[2]; vp[1] = vp[3];
      } else if (ps == 1) {
        TS(13);
        nb_sync(NB_WG0, 128);
        contract(kc, stg0, 0);
        mbar_wait(BAR(MB_UFULL));
        TS(15);
        nb_sync(NB_HAND, 256);
        af[0] = lds128(hand); af[1] = lds128(hand + 512); vp[0] = lds128(hand + 1024); vp[1] = lds128(hand + 1536);
        nb_sync(NB_WG0, 128);
      }
    }
    TS(wg * 16 + 14);
    float p[4][8];
    if (wg) {
      nb_arrive(NB_ST0, 256);
      nb_arrive(NB_GATE, 256);
    } else {
      uint32_t* pz = (uint32_t*)(pp - t + 128) + w * 16 + c * 8 + g;
      asm volatile("" : "+l"(pp), "+l"(pz));
      nb_sync(NB_ST0, 256);
      contract(kc, stg1, 1);
      TS(6);
      float kv[8];
#pragma unroll
      for (int i = 0; i < 8; i++) kv[i] = w & 2 ? kc[8 + i] : kc[i];
      st_x(pp, nz(pack_bf(kv[0], kv[1])), pack_bf(kv[2], kv[3]), pack_bf(kv[4], kv[5]), pack_bf(kv[6], kv[7]));
      if (c < 2) st_x32(pz, nz(fu(c ? kc[18] : kc[16])));
      TS(5);
    }
    SPLIT();
    WG_FENCE();
#pragma unroll
    for (int u = 0; u < 4; u++) wgmma_rs_n16(p[u], aq[u], qdesc(sb + OFF_PHI + (u & 1) * 512), 0);
    WG_COMMIT();
    WG_WAIT(0);
#pragma unroll
    for (int u = 0; u < 4; u++) {
      const uint32_t pw[4] = {pack_bf(p[u][0], p[u][2]), pack_bf(p[u][1], p[u][3]), pack_bf(p[u][4], p[u][6]), pack_bf(p[u][5], p[u][7])};
      dual_exp(pw, eq + 8 * u);
    }
    SPLIT();
  }
  TS(wg * 16 + 4);
  if (wg == 1) {
    mbar_wait(BAR(MB_UFULL));
    const uint4* ps = g_part + (size_t)hp * 8 * 144 + t;
    const uint32_t* zs = (const uint32_t*)(g_part + (size_t)(hp * 8 + (lane >> 4) * 4) * 144 + 128) + w * 16 + (lane & 15);
    uint4 v[8];
    uint32_t zv[4];
#pragma unroll 1
    for (int it = 0; it < SPIN_MAX; it++) {
#pragma unroll
      for (int i = 0; i < 8; i++) v[i] = ld_x(ps + i * 144);
#pragma unroll
      for (int i = 0; i < 4; i++) zv[i] = ld_x32(zs + i * 576);
      uint32_t m = min(min(zv[0], zv[1]), min(zv[2], zv[3]));
#pragma unroll
      for (int i = 0; i < 8; i++) m = min(m, v[i].x);
      if (__all_sync(0xffffffffu, m != 0)) break;
    }
    float s[8];
    WG_FENCE();
#pragma unroll
    for (int r = 0; r < 8; r++) wgmma_rs_n16(s, v[r], qdesc(sb + OFF_EYE), r);
    WG_COMMIT();
    float zsum = (uf(zv[0]) + uf(zv[1])) + (uf(zv[2]) + uf(zv[3]));
    zsum += __shfl_xor_sync(0xffffffffu, zsum, 16);
    const uint32_t z1 = pack_bf(zsum, 1.f);
    if (lane < 16) sts128(kvs + w * 768 + 512 + lane * 16, z1, z1, z1, z1);
    WG_WAIT(0);
    stsm4(kvs + w * 768 + lane * 16, pack_bf(s[0], s[1]), pack_bf(s[2], s[3]), pack_bf(s[4], s[5]), pack_bf(s[6], s[7]));
    asm volatile("fence.proxy.async.shared::cta;" ::: "memory");
    TS(22);
  }
  nb_sync(NB_KV, 256);
  {
    float n[8][12];
    WG_FENCE();
#pragma unroll
    for (int i = 0; i < 8; i++) wgmma_rs_n24(n[i], make_uint4(eq[4 * i], eq[4 * i + 1], eq[4 * i + 2], eq[4 * i + 3]), qdesc(kvs + (i & 3) * 768), 0);
    WG_COMMIT();
    uint32_t* od = (uint32_t*)(g_o + (size_t)((rt * 4 + wg * 2) * 32 + hp * 2) * 128) + w * 64 + lane;
    WG_WAIT(0);
#pragma unroll
    for (int u = 0; u < 4; u++) {
      float(&np)[12] = n[2 * u];
      const float(&nm)[12] = n[2 * u + 1];
      const float q0 = np[9] * rcp(nm[9]), q1 = np[11] * rcp(nm[11]);
      const float r0 = rcp(fmaf(nm[8], q0, fmaf(np[9], 1e-6f, np[8]))), r1 = rcp(fmaf(nm[10], q1, fmaf(np[11], 1e-6f, np[10])));
#pragma unroll
      for (int i = 0; i < 8; i++) np[i] = fmaf(nm[i], (i & 2) ? q1 : q0, np[i]);
      uint32_t* o = od + (u >> 1) * 16384 + (u & 1) * 512;
      o[0] = pack_bf(np[0] * r0, np[1] * r0);
      o[32] = pack_bf(np[2] * r1, np[3] * r1);
      o[256] = pack_bf(np[4] * r0, np[5] * r0);
      o[288] = pack_bf(np[6] * r1, np[7] * r1);
      if (u == 1) SPLIT();
    }
  }
  TS(wg * 16 + 7);
  nb_arrive(NB_ODONE, 288);
  if (wg) {
    const uint4* src = P.xs + X_Y + (oct * 32 + c * 8) * 256 + (2 * w + (g >> 2)) * 32 + i8 * 4 + (g & 3);
    __nv_bfloat16* dst = P.out + (size_t)((2 * w + (g >> 2)) * 256 + i8 * 16 + (g & 3) * 2) * 1024 + 512 + oct * 32 + c * 8;
    nb_sync(NB_GATE + 1, 160);
    nb_sync(NB_Y + w, 160);
    uint4 v[8];
#pragma unroll 1
    for (int it = 0; it < SPIN_MAX; it++) {
      uint32_t m = 0xffffffffu;
#pragma unroll
      for (int i = 0; i < 8; i++) v[i] = ld_x(src + i * 256);
#pragma unroll
      for (int i = 0; i < 8; i++) m = min(m, v[i].x);
      if (__all_sync(0xffffffffu, m != 0)) break;
    }
#pragma unroll
    for (int i = 0; i < 8; i++) *(uint4*)(dst + (size_t)((i >> 2) * 128 + ((i >> 1) & 1) * 8 + (i & 1)) * 1024) = tr_row(v, i);
    TS(31);
    GT(63);
    if (w == 0) TSDUMP(16);
    return;
  }
  mbar_wait(BAR(MB_WO));
  nb_sync(NB_BDONE, 288);
  TS(8);
  mbar_spin(BAR(MB_O));
  TS(9);
  constexpr uint64_t ha = mkdesc(0, 0, 128, 0), hb = mkdesc(0, 0, 1024, 1);
  constexpr uint32_t da0 = (uint32_t)mkdesc(stg1, 1024, 0, 0), db0 = (uint32_t)mkdesc(sb + OFF_W, 8192, 0, 0);
  const uint32_t ot = ((sb + OFF_T + 1023) & ~1023u) + w * 4096;
  auto store_half = [&](const float* oc, int hf) {
#pragma unroll
    for (int i = 0; i < 8; i += 2)
      stsm4(ot + hf * 2048 + (lane & 15) * 128 + (((i + (lane >> 4)) ^ lane) & 7) * 16, pack_bf(oc[4 * i], oc[4 * i + 1]),
            pack_bf(oc[4 * i + 2], oc[4 * i + 3]), pack_bf(oc[4 * i + 4], oc[4 * i + 5]), pack_bf(oc[4 * i + 6], oc[4 * i + 7]));
    asm volatile("fence.proxy.async.shared::cta;" ::: "memory");
    __syncwarp();
    e_store2d(&mout, ot + hf * 2048, (hp & 3) * 128 + hf * 64, (rt * 4 + (hp >> 2)) * 64 + w * 16);
  };
  float oc[64];
#pragma unroll 1
  for (int j = 0; j < 8; j++) {
    const int kb = (j + 7) & 7;
    if ((j & 1) && j < 6) mbar_spin(BAR(MB_O + 1) + 4 * (j - 1));
    WG_FENCE();
#pragma unroll
    for (int k = 0; k < 4; k++) wgmma_ss_n128(oc, ha | (da0 + 512 * kb + 128 * k), hb | (db0 + 1024 * kb + 128 * k), k ? 1 : j);
    WG_COMMIT();
  }
  WG_WAIT(0);
  TS(10);
  store_half(oc, 0);
  store_half(oc + 32, 1);
  asm volatile(ELECT "cp.async.bulk.commit_group;\n@p cp.async.bulk.wait_group.read 0;\n}\n" ::: "memory");
  TS(wg * 16 + 11);
  GT(61 + wg);
  if (w == 0) TSDUMP(0);
  if (w == 1) TSDUMP(48);
}

typedef CUresult (*EncodeFn)(CUtensorMap*, CUtensorMapDataType, cuuint32_t, void*, const cuuint64_t*, const cuuint64_t*,
                             const cuuint32_t*, const cuuint32_t*, CUtensorMapInterleave, CUtensorMapSwizzle,
                             CUtensorMapL2promotion, CUtensorMapFloatOOBfill);

}

extern "C" void kernel_launch(void* const* d_in, const int* in_sizes, int n_in, void* d_out, int out_size) {
  (void)in_sizes; (void)n_in; (void)out_size;
  void* fn = nullptr;
  cudaDriverEntryPointQueryResult qr;
  cudaGetDriverEntryPoint("cuTensorMapEncodeTiled", &fn, cudaEnableDefault, &qr);
  EncodeFn enc = (EncodeFn)fn;
  CUtensorMap mx, mw, mo, mu, mout;
  const cuuint32_t es[5] = {1, 1, 1, 1, 1};
  {
    cuuint64_t dims[2] = {512, 2048}, st[1] = {1024};
    cuuint32_t box[2] = {64, 128};
    enc(&mx, CU_TENSOR_MAP_DATA_TYPE_BFLOAT16, 2, d_in[0], dims, st, box, es, CU_TENSOR_MAP_INTERLEAVE_NONE,
        CU_TENSOR_MAP_SWIZZLE_128B, CU_TENSOR_MAP_L2_PROMOTION_L2_128B, CU_TENSOR_MAP_FLOAT_OOB_FILL_NONE);
  }
  {
    cuuint64_t dims[3] = {512, 512, 3}, st[2] = {3072, 1024};
    cuuint32_t box[3] = {32, 64, 3};
    enc(&mw, CU_TENSOR_MAP_DATA_TYPE_BFLOAT16, 3, d_in[1], dims, st, box, es, CU_TENSOR_MAP_INTERLEAVE_NONE,
        CU_TENSOR_MAP_SWIZZLE_64B, CU_TENSOR_MAP_L2_PROMOTION_L2_128B, CU_TENSOR_MAP_FLOAT_OOB_FILL_NONE);
  }
  {
    cuuint64_t dims[3] = {64, 512, 8}, st[2] = {1024, 128};
    cuuint32_t box[3] = {64, 64, 2};
    enc(&mo, CU_TENSOR_MAP_DATA_TYPE_BFLOAT16, 3, d_in[3], dims, st, box, es, CU_TENSOR_MAP_INTERLEAVE_NONE,
        CU_TENSOR_MAP_SWIZZLE_128B, CU_TENSOR_MAP_L2_PROMOTION_L2_128B, CU_TENSOR_MAP_FLOAT_OOB_FILL_NONE);
  }
  {
    cuuint64_t dims[4] = {512, 4, 16, 32}, st[3] = {16384, 1024, 65536};
    cuuint32_t box[4] = {64, 4, 16, 2};
    enc(&mu, CU_TENSOR_MAP_DATA_TYPE_BFLOAT16, 4, d_in[4], dims, st, box, es, CU_TENSOR_MAP_INTERLEAVE_NONE,
        CU_TENSOR_MAP_SWIZZLE_128B, CU_TENSOR_MAP_L2_PROMOTION_L2_128B, CU_TENSOR_MAP_FLOAT_OOB_FILL_NONE);
  }
  {
    cuuint64_t dims[2] = {1024, 2048}, st[1] = {2048};
    cuuint32_t box[2] = {64, 16};
    enc(&mout, CU_TENSOR_MAP_DATA_TYPE_BFLOAT16, 2, d_out, dims, st, box, es, CU_TENSOR_MAP_INTERLEAVE_NONE,
        CU_TENSOR_MAP_SWIZZLE_128B, CU_TENSOR_MAP_L2_PROMOTION_NONE, CU_TENSOR_MAP_FLOAT_OOB_FILL_NONE);
  }
  Params P;
  P.x = (const __nv_bfloat16*)d_in[0];
  P.wphi = (const __nv_bfloat16*)d_in[2];
  P.wo = (const __nv_bfloat16*)d_in[3];
  P.logA = (const __nv_bfloat16*)d_in[5];
  P.Aim = (const __nv_bfloat16*)d_in[6];
  P.Cre = (const __nv_bfloat16*)d_in[7];
  P.Cim = (const __nv_bfloat16*)d_in[8];
  P.logdt = (const __nv_bfloat16*)d_in[9];
  P.Dskip = (const __nv_bfloat16*)d_in[10];
  P.out = (__nv_bfloat16*)d_out;
  cudaGetSymbolAddress((void**)&P.xs, g_x);
  P.ts = nullptr;
  cudaFuncSetAttribute(fused_kernel, cudaFuncAttributeMaxDynamicSharedMemorySize, SMEM_BYTES);
  fused_kernel<<<NCTA, NTHREADS, SMEM_BYTES>>>(P, mx, mw, mo, mu, mout);
}
```

```cpp
#include <cuda_runtime.h>
#include <cuda_bf16.h>
#include <cuda_fp16.h>
#include <cuda.h>
#include <stdint.h>
#include <type_traits>

#define DBG_TS 0

namespace {

constexpr int NTHREADS = 512;
constexpr int NCTA = 128;
constexpr int OFF_W = 0;
constexpr int OFF_X = 98304;
constexpr int OFF_U = OFF_X + 65536;
constexpr int U_CH = 4416, U_ODD = 2240, U_PAD = 128;
constexpr int OFF_STG0 = OFF_U + 18432;
constexpr int SLAB = 3328;
constexpr int OFF_T = OFF_STG0 + 8 * SLAB;
constexpr int T_CH = 5216;
constexpr int T_D = 0;
constexpr int T_5 = 2144;
constexpr int T_3 = T_5 + 384;
constexpr int T_7 = T_5 + 1024;
constexpr int T_9 = T_7 + 320;
constexpr int T_KC = T_9 + 320;
constexpr int T_ST = T_5 - 1024;
constexpr int OFF_PHI = OFF_T + 4 * T_CH;
constexpr int OFF_EYE = OFF_PHI + 1024, OFF_ONE = OFF_EYE + 512;
constexpr int OFF_BAR = OFF_ONE + 256;
constexpr int SMEM_BYTES = OFF_BAR + 512 + 256 * DBG_TS;
constexpr uint32_t SB = 1024;
static_assert(T_KC + 2 * 656 <= T_CH, "table size");
static_assert(SMEM_BYTES <= 232448, "smem");
constexpr int MB_URAW = 0, MB_FULL = 1  , MB_WO = 17, MB_UFULL = 18, MB_O = 19  ,
              MB_EMPTY = 23  , MB_AUX = 39;
__host__ __device__ constexpr uint32_t BAR(int i) { return SB + OFF_BAR + 8 * i; }
constexpr int NB_WG0 = 1, NB_ODONE = 2, NB_ST0 = 3, NB_HAND = 4, NB_KV = 5, NB_YZ = 6, NB_INIT = 7, NB_PREP = 8, NB_PROD = 9, NB_KREAD = 10,
              NB_BDONE = 11, NB_GATE = 12  , NB_Y = 7  ;
#define GATEV 1
constexpr int U_AT = 2;
constexpr int ZERO_STEP = 12;
constexpr int SPIN_MAX = 1 << 16;

constexpr int X_CNT = 0;
constexpr int X_PART = 256;
constexpr int X_O = X_PART + 16 * 8 * 144;
constexpr int X_Y = X_O + 32 * 32 * 128;
constexpr int X_UT = X_Y + 512 * 8 * 32;
constexpr int X_SIZE = X_UT + 512 * (U_CH / 16);
__device__ __align__(128) uint4 g_x[X_SIZE];
extern __shared__ uint8_t smem_raw[];
#define TS(i) do {} while (0)
#define TS1(i) do {} while (0)
#define GT(i) do {} while (0)
#define TSDUMP(base) do {} while (0)

__device__ __forceinline__ uint32_t smem_u32(const void* p) { return (uint32_t)__cvta_generic_to_shared(p); }
__device__ __forceinline__ void mbar_arrive(uint32_t b) {
  asm volatile("mbarrier.arrive.shared::cta.b64 _, [%0];" ::"r"(b) : "memory");
}
__device__ __forceinline__ void mbar_wait(uint32_t b) {
  uint32_t done = 0;
#pragma unroll 1
  for (int i = 0; i < SPIN_MAX && !done; i++) {
    asm volatile("{\n.reg .pred p;\nmbarrier.try_wait.parity.shared::cta.b64 p, [%1], 0, 4000;\nselp.u32 %0, 1, 0, p;\n}\n"
                 : "=r"(done) : "r"(b) : "memory");
  }
}
__device__ __forceinline__ void mbar_spin(uint32_t b) {
  uint32_t done = 0;
#pragma unroll 1
  for (int i = 0; i < (SPIN_MAX << 4) && !done; i++) {
    asm volatile("{\n.reg .pred p;\nmbarrier.try_wait.parity.shared::cta.b64 p, [%1], 0;\nselp.u32 %0, 1, 0, p;\n}\n"
                 : "=r"(done) : "r"(b) : "memory");
  }
}
__device__ __forceinline__ void mbar_init(uint32_t b, int n) {
  asm volatile("mbarrier.init.shared::cta.b64 [%0], %1;" ::"r"(b), "r"(n) : "memory");
}
__device__ __forceinline__ void mbar_expect(uint32_t b, int bytes) {
  asm volatile("mbarrier.arrive.expect_tx.shared::cta.b64 _, [%0], %1;" ::"r"(b), "r"(bytes) : "memory");
}
__device__ __forceinline__ void nb_sync(int id, int n) { asm volatile("bar.sync %0, %1;" ::"r"(id), "r"(n) : "memory"); }
__device__ __forceinline__ void nb_arrive(int id, int n) { asm volatile("bar.arrive %0, %1;" ::"r"(id), "r"(n) : "memory"); }
#define ELECT "{\n.reg .pred p;\nelect.sync _|p, 0xffffffff;\n@p "
__device__ __forceinline__ void e_arrive(uint32_t b) {
  asm volatile(ELECT "mbarrier.arrive.shared::cta.b64 _, [%0];\n}\n" ::"r"(b) : "memory");
}
__device__ __forceinline__ void e_expect(uint32_t b, int bytes) {
  asm volatile(ELECT "mbarrier.arrive.expect_tx.shared::cta.b64 _, [%0], %1;\n}\n" ::"r"(b), "r"(bytes) : "memory");
}
__device__ __forceinline__ void e_tma2d(uint32_t dst, const CUtensorMap* m, uint32_t bar, int c0, int c1) {
  asm volatile(ELECT "cp.async.bulk.tensor.2d.shared::cluster.global.mbarrier::complete_tx::bytes [%0], [%1, {%3,%4}], [%2];\n}\n"
               ::"r"(dst), "l"(m), "r"(bar), "r"(c0), "r"(c1) : "memory");
}
__device__ __forceinline__ void e_tma3d(uint32_t dst, const CUtensorMap* m, uint32_t bar, int c0, int c1, int c2) {
  asm volatile(ELECT "cp.async.bulk.tensor.3d.shared::cluster.global.mbarrier::complete_tx::bytes [%0], [%1, {%3,%4,%5}], [%2];\n}\n"
               ::"r"(dst), "l"(m), "r"(bar), "r"(c0), "r"(c1), "r"(c2) : "memory");
}
__device__ __forceinline__ void e_tma4d(uint32_t dst, const CUtensorMap* m, uint32_t bar, int c0, int c3) {
  asm volatile(ELECT "cp.async.bulk.tensor.4d.shared::cluster.global.mbarrier::complete_tx::bytes [%0], [%1, {%3,%5,%5,%4}], [%2];\n}\n"
               ::"r"(dst), "l"(m), "r"(bar), "r"(c0), "r"(c3), "r"(0) : "memory");
}
__device__ __forceinline__ void e_bulk(uint32_t dst, const void* src, int bytes, uint32_t bar) {
  asm volatile(ELECT "cp.async.bulk.shared::cluster.global.mbarrier::complete_tx::bytes [%0], [%1], %2, [%3];\n}\n"
               ::"r"(dst), "l"(src), "r"(bytes), "r"(bar) : "memory");
}
__device__ __forceinline__ void e_prefetch(const void* p, int bytes) {
  asm volatile(ELECT "cp.async.bulk.prefetch.L2.global [%0], %1;\n}\n" ::"l"(p), "r"(bytes) : "memory");
}
__device__ __forceinline__ void e_store2d(const CUtensorMap* m, uint32_t src, int c0, int c1) {
  asm volatile(ELECT "cp.async.bulk.tensor.2d.global.shared::cta.bulk_group [%0, {%2,%3}], [%1];\n}\n"
               ::"l"(m), "r"(src), "r"(c0), "r"(c1) : "memory");
}
__host__ __device__ constexpr uint64_t mkdesc(uint32_t addr, uint32_t lbo, uint32_t sbo, int swz) {
  return (uint64_t)((addr & 0x3FFFF) >> 4) | ((uint64_t)(lbo >> 4) << 16) | ((uint64_t)(sbo >> 4) << 32) |
         ((uint64_t)swz << 62);
}
#define SPLIT() asm volatile("{\n.reg .pred p;\nsetp.eq.u32 p, %0, %1;\n@p exit;\n}\n" ::"r"(blockIdx.y), "n"(__LINE__) : "memory")
#define SPLITN(n) asm volatile("{\n.reg .pred p;\nsetp.eq.u32 p, %0, %1;\n@p exit;\n}\n" ::"r"(blockIdx.y), "r"(4096 + (n)) : "memory")
#define WG_FENCE() asm volatile("wgmma.fence.sync.aligned;" ::: "memory")
#define WG_COMMIT() asm volatile("wgmma.commit_group.sync.aligned;" ::: "memory")
#define WG_WAIT(n) asm volatile("wgmma.wait_group.sync.aligned " #n ";" ::: "memory")

__device__ __forceinline__ void mma(float& d0, float& d1, float& d2, float& d3, uint32_t a0, uint32_t a1, uint32_t a2,
                                    uint32_t a3, uint32_t b0, uint32_t b1) {
  asm volatile("mma.sync.aligned.m16n8k16.row.col.f32.bf16.bf16.f32 {%0,%1,%2,%3},{%4,%5,%6,%7},{%8,%9},{%0,%1,%2,%3};"
               : "+f"(d0), "+f"(d1), "+f"(d2), "+f"(d3)
               : "r"(a0), "r"(a1), "r"(a2), "r"(a3), "r"(b0), "r"(b1));
}
__device__ __forceinline__ void mmac(float (&d)[4], uint32_t a0, uint32_t a1, uint32_t a2, uint32_t a3, uint32_t b0,
                                     uint32_t b1, const float (&c)[4]) {
  asm volatile("mma.sync.aligned.m16n8k16.row.col.f32.bf16.bf16.f32 {%0,%1,%2,%3},{%4,%5,%6,%7},{%8,%9},{%10,%11,%12,%13};"
               : "=f"(d[0]), "=f"(d[1]), "=f"(d[2]), "=f"(d[3])
               : "r"(a0), "r"(a1), "r"(a2), "r"(a3), "r"(b0), "r"(b1), "f"(c[0]), "f"(c[1]), "f"(c[2]), "f"(c[3]));
}
__device__ __forceinline__ void mma_h(float (&d)[4], const uint32_t (&a)[4], uint32_t b0, uint32_t b1) {
  asm volatile("mma.sync.aligned.m16n8k16.row.col.f32.f16.f16.f32 {%0,%1,%2,%3},{%4,%5,%6,%7},{%8,%9},{%0,%1,%2,%3};"
               : "+f"(d[0]), "+f"(d[1]), "+f"(d[2]), "+f"(d[3]) : "r"(a[0]), "r"(a[1]), "r"(a[2]), "r"(a[3]), "r"(b0), "r"(b1));
}
__device__ __forceinline__ void mma0(float& d0, float& d1, float& d2, float& d3, uint32_t a0, uint32_t a1, uint32_t a2,
                                     uint32_t a3, uint32_t b0, uint32_t b1) {
  asm volatile("mma.sync.aligned.m16n8k16.row.col.f32.bf16.bf16.f32 {%0,%1,%2,%3},{%4,%5,%6,%7},{%8,%9},{%10,%10,%10,%10};"
               : "=f"(d0), "=f"(d1), "=f"(d2), "=f"(d3)
               : "r"(a0), "r"(a1), "r"(a2), "r"(a3), "r"(b0), "r"(b1), "f"(0.f));
}
__device__ __forceinline__ uint32_t pack_bf(float lo, float hi) {
  uint32_t r;
  asm("cvt.rn.bf16x2.f32 %0, %1, %2;" : "=r"(r) : "f"(hi), "f"(lo));
  return r;
}
__device__ __forceinline__ float bf_lo(uint32_t w) { return __uint_as_float(w << 16); }
__device__ __forceinline__ float bf_hi(uint32_t w) { return __uint_as_float(w & 0xffff0000u); }
__device__ __forceinline__ float bf_round(float x) { return __bfloat162float(__float2bfloat16_rn(x)); }
__device__ __forceinline__ uint32_t bmax2(uint32_t a, uint32_t b) {
  uint32_t r; asm("max.bf16x2 %0, %1, %2;" : "=r"(r) : "r"(a), "r"(b)); return r;
}
__device__ __forceinline__ uint32_t bmin2(uint32_t a, uint32_t b) {
  uint32_t r; asm("min.bf16x2 %0, %1, %2;" : "=r"(r) : "r"(a), "r"(b)); return r;
}
__device__ __forceinline__ float ex2(float x) { float r; asm("ex2.approx.ftz.f32 %0, %1;" : "=f"(r) : "f"(x)); return r; }
__device__ __forceinline__ float rcp(float x) { float r; asm("rcp.approx.ftz.f32 %0, %1;" : "=f"(r) : "f"(x)); return r; }
__device__ __forceinline__ void ldsm4(uint32_t (&r)[4], uint32_t a) {
  asm volatile("ldmatrix.sync.aligned.m8n8.x4.shared.b16 {%0,%1,%2,%3}, [%4];"
               : "=r"(r[0]), "=r"(r[1]), "=r"(r[2]), "=r"(r[3]) : "r"(a) : "memory");
}
__device__ __forceinline__ void ldsm4t(uint32_t (&r)[4], uint32_t a) {
  asm volatile("ldmatrix.sync.aligned.m8n8.x4.trans.shared.b16 {%0,%1,%2,%3}, [%4];"
               : "=r"(r[0]), "=r"(r[1]), "=r"(r[2]), "=r"(r[3]) : "r"(a) : "memory");
}
__device__ __forceinline__ void stsm4(uint32_t a, uint32_t r0, uint32_t r1, uint32_t r2, uint32_t r3) {
  asm volatile("stmatrix.sync.aligned.m8n8.x4.shared.b16 [%0], {%1,%2,%3,%4};"
               ::"r"(a), "r"(r0), "r"(r1), "r"(r2), "r"(r3) : "memory");
}
__device__ __forceinline__ uint32_t lds32(uint32_t a) {
  uint32_t r; asm volatile("ld.shared.u32 %0, [%1];" : "=r"(r) : "r"(a) : "memory"); return r;
}
__device__ __forceinline__ uint32_t lds16(uint32_t a) {
  uint32_t r; asm volatile("{\n.reg .u16 h;\nld.shared.u16 h, [%1];\ncvt.u32.u16 %0, h;\n}\n" : "=r"(r) : "r"(a) : "memory"); return r;
}
__device__ __forceinline__ uint2 lds64(uint32_t a) {
  uint2 r; asm volatile("ld.shared.v2.u32 {%0,%1}, [%2];" : "=r"(r.x), "=r"(r.y) : "r"(a) : "memory"); return r;
}
__device__ __forceinline__ uint4 lds128(uint32_t a) {
  uint4 r;
  asm volatile("ld.shared.v4.u32 {%0,%1,%2,%3}, [%4];" : "=r"(r.x), "=r"(r.y), "=r"(r.z), "=r"(r.w) : "r"(a) : "memory");
  return r;
}
__device__ __forceinline__ void sts32(uint32_t a, uint32_t v) { asm volatile("st.shared.u32 [%0], %1;" ::"r"(a), "r"(v) : "memory"); }
__device__ __forceinline__ void sts16(uint32_t a, uint32_t v) {
  asm volatile("{\n.reg .u16 h;\ncvt.u16.u32 h, %1;\nst.shared.u16 [%0], h;\n}\n" ::"r"(a), "r"(v) : "memory");
}
__device__ __forceinline__ void sts64(uint32_t a, uint32_t x, uint32_t y) {
  asm volatile("st.shared.v2.u32 [%0], {%1,%2};" ::"r"(a), "r"(x), "r"(y) : "memory");
}
__device__ __forceinline__ void sts128(uint32_t a, uint32_t x, uint32_t y, uint32_t z, uint32_t w) {
  asm volatile("st.shared.v4.u32 [%0], {%1,%2,%3,%4};" ::"r"(a), "r"(x), "r"(y), "r"(z), "r"(w) : "memory");
}
__device__ __forceinline__ uint4 ld_x(const uint4* p) {
  uint4 r;
  asm volatile("{\n.reg .b128 t;\nld.relaxed.gpu.global.b128 t, [%4];\nmov.b128 {%0,%1,%2,%3}, t;\n}\n"
               : "=r"(r.x), "=r"(r.y), "=r"(r.z), "=r"(r.w) : "l"(p) : "memory");
  return r;
}
__device__ __forceinline__ uint32_t ld_x32(const uint32_t* p) {
  uint32_t r; asm volatile("ld.relaxed.gpu.global.u32 %0, [%1];" : "=r"(r) : "l"(p) : "memory"); return r;
}
__device__ __forceinline__ void st_x(uint4* p, uint32_t x, uint32_t y, uint32_t z, uint32_t w) {
  asm volatile("{\n.reg .b128 t;\nmov.b128 t, {%1,%2,%3,%4};\nst.relaxed.gpu.global.b128 [%0], t;\n}\n"
               ::"l"(p), "r"(x), "r"(y), "r"(z), "r"(w) : "memory");
}
__device__ __forceinline__ void st_x32(uint32_t* p, uint32_t x) {
  asm volatile("st.relaxed.gpu.global.u32 [%0], %1;" ::"l"(p), "r"(x) : "memory");
}
__device__ __forceinline__ uint32_t nz(uint32_t w) { return max(w, 1u); }
__device__ __forceinline__ uint32_t fu(float x) { return __float_as_uint(x); }
__device__ __forceinline__ float uf(uint32_t x) { return __uint_as_float(x); }

__device__ __forceinline__ void wgmma_ss_n96(float (&d)[48], uint64_t da, uint64_t db, int sc) {
  asm volatile("{\n.reg .pred p;\nsetp.ne.b32 p, %50, 0;\n"
      "wgmma.mma_async.sync.aligned.m64n96k16.f32.bf16.bf16 "
      "{%0,%1,%2,%3,%4,%5,%6,%7,%8,%9,%10,%11,%12,%13,%14,%15,%16,%17,%18,%19,%20,%21,%22,%23,%24,%25,%26,%27,%28,%29,%30,%31,%32,%33,%34,%35,%36,%37,%38,%39,%40,%41,%42,%43,%44,%45,%46,%47}, "
      "%48, %49, p, 1, 1, 0, 1;\n}\n"
      : "+f"(d[0]), "+f"(d[1]), "+f"(d[2]), "+f"(d[3]), "+f"(d[4]), "+f"(d[5]), "+f"(d[6]), "+f"(d[7]),
        "+f"(d[8]), "+f"(d[9]), "+f"(d[10]), "+f"(d[11]), "+f"(d[12]), "+f"(d[13]), "+f"(d[14]), "+f"(d[15]),
        "+f"(d[16]), "+f"(d[17]), "+f"(d[18]), "+f"(d[19]), "+f"(d[20]), "+f"(d[21]), "+f"(d[22]), "+f"(d[23]),
        "+f"(d[24]), "+f"(d[25]), "+f"(d[26]), "+f"(d[27]), "+f"(d[28]), "+f"(d[29]), "+f"(d[30]), "+f"(d[31]),
        "+f"(d[32]), "+f"(d[33]), "+f"(d[34]), "+f"(d[35]), "+f"(d[36]), "+f"(d[37]), "+f"(d[38]), "+f"(d[39]),
        "+f"(d[40]), "+f"(d[41]), "+f"(d[42]), "+f"(d[43]), "+f"(d[44]), "+f"(d[45]), "+f"(d[46]), "+f"(d[47])
      : "l"(da), "l"(db), "r"(sc));
}

__device__ __forceinline__ void wgmma_ss_n128(float (&d)[64], uint64_t da, uint64_t db, int sc) {
  asm volatile("{\n.reg .pred p;\nsetp.ne.b32 p, %66, 0;\n"
      "wgmma.mma_async.sync.aligned.m64n128k16.f32.bf16.bf16 "
      "{%0,%1,%2,%3,%4,%5,%6,%7,%8,%9,%10,%11,%12,%13,%14,%15,%16,%17,%18,%19,%20,%21,%22,%23,%24,%25,%26,%27,%28,%29,%30,%31,%32,%33,%34,%35,%36,%37,%38,%39,%40,%41,%42,%43,%44,%45,%46,%47,%48,%49,%50,%51,%52,%53,%54,%55,%56,%57,%58,%59,%60,%61,%62,%63}, "
      "%64, %65, p, 1, 1, 0, 1;\n}\n"
      : "+f"(d[0]), "+f"(d[1]), "+f"(d[2]), "+f"(d[3]), "+f"(d[4]), "+f"(d[5]), "+f"(d[6]), "+f"(d[7]),
        "+f"(d[8]), "+f"(d[9]), "+f"(d[10]), "+f"(d[11]), "+f"(d[12]), "+f"(d[13]), "+f"(d[14]), "+f"(d[15]),
        "+f"(d[16]), "+f"(d[17]), "+f"(d[18]), "+f"(d[19]), "+f"(d[20]), "+f"(d[21]), "+f"(d[22]), "+f"(d[23]),
        "+f"(d[24]), "+f"(d[25]), "+f"(d[26]), "+f"(d[27]), "+f"(d[28]), "+f"(d[29]), "+f"(d[30]), "+f"(d[31]),
        "+f"(d[32]), "+f"(d[33]), "+f"(d[34]), "+f"(d[35]), "+f"(d[36]), "+f"(d[37]), "+f"(d[38]), "+f"(d[39]),
        "+f"(d[40]), "+f"(d[41]), "+f"(d[42]), "+f"(d[43]), "+f"(d[44]), "+f"(d[45]), "+f"(d[46]), "+f"(d[47]),
        "+f"(d[48]), "+f"(d[49]), "+f"(d[50]), "+f"(d[51]), "+f"(d[52]), "+f"(d[53]), "+f"(d[54]), "+f"(d[55]),
        "+f"(d[56]), "+f"(d[57]), "+f"(d[58]), "+f"(d[59]), "+f"(d[60]), "+f"(d[61]), "+f"(d[62]), "+f"(d[63])
      : "l"(da), "l"(db), "r"(sc));
}

__device__ __forceinline__ void wgmma_ss_n40(float (&d)[20], uint64_t da, uint64_t db, int sc) {
  asm volatile("{\n.reg .pred p;\nsetp.ne.b32 p, %22, 0;\n"
      "wgmma.mma_async.sync.aligned.m64n40k16.f32.bf16.bf16 "
      "{%0,%1,%2,%3,%4,%5,%6,%7,%8,%9,%10,%11,%12,%13,%14,%15,%16,%17,%18,%19}, "
      "%20, %21, p, 1, 1, 1, 1;\n}\n"
      : "+f"(d[0]), "+f"(d[1]), "+f"(d[2]), "+f"(d[3]), "+f"(d[4]), "+f"(d[5]), "+f"(d[6]), "+f"(d[7]),
        "+f"(d[8]), "+f"(d[9]), "+f"(d[10]), "+f"(d[11]), "+f"(d[12]), "+f"(d[13]), "+f"(d[14]), "+f"(d[15]),
        "+f"(d[16]), "+f"(d[17]), "+f"(d[18]), "+f"(d[19])
      : "l"(da), "l"(db), "r"(sc));
}

__device__ __forceinline__ void wgmma_rs_n8(float (&d)[4], const uint4& a, uint64_t db, int sc) {
  asm volatile("{\n.reg .pred p;\nsetp.ne.b32 p, %9, 0;\n"
      "wgmma.mma_async.sync.aligned.m64n8k16.f32.bf16.bf16 "
      "{%0,%1,%2,%3}, "
      "{%4,%5,%6,%7}, %8, p, 1, 1, 1;\n}\n"
      : "+f"(d[0]), "+f"(d[1]), "+f"(d[2]), "+f"(d[3])
      : "r"(a.x), "r"(a.y), "r"(a.z), "r"(a.w), "l"(db), "r"(sc));
}

__device__ __forceinline__ void wgmma_rs_n16(float (&d)[8], const uint4& a, uint64_t db, int sc) {
  asm volatile("{\n.reg .pred p;\nsetp.ne.b32 p, %13, 0;\n"
      "wgmma.mma_async.sync.aligned.m64n16k16.f32.bf16.bf16 "
      "{%0,%1,%2,%3,%4,%5,%6,%7}, "
      "{%8,%9,%10,%11}, %12, p, 1, 1, 1;\n}\n"
      : "+f"(d[0]), "+f"(d[1]), "+f"(d[2]), "+f"(d[3]), "+f"(d[4]), "+f"(d[5]), "+f"(d[6]), "+f"(d[7])
      : "r"(a.x), "r"(a.y), "r"(a.z), "r"(a.w), "l"(db), "r"(sc));
}

__device__ __forceinline__ void wgmma_rs_n24(float (&d)[12], const uint4& a, uint64_t db, int sc) {
  asm volatile("{\n.reg .pred p;\nsetp.ne.b32 p, %17, 0;\n"
      "wgmma.mma_async.sync.aligned.m64n24k16.f32.bf16.bf16 "
      "{%0,%1,%2,%3,%4,%5,%6,%7,%8,%9,%10,%11}, "
      "{%12,%13,%14,%15}, %16, p, 1, 1, 1;\n}\n"
      : "+f"(d[0]), "+f"(d[1]), "+f"(d[2]), "+f"(d[3]), "+f"(d[4]), "+f"(d[5]), "+f"(d[6]), "+f"(d[7]),
        "+f"(d[8]), "+f"(d[9]), "+f"(d[10]), "+f"(d[11])
      : "r"(a.x), "r"(a.y), "r"(a.z), "r"(a.w), "l"(db), "r"(sc));
}

struct Params {
  const __nv_bfloat16 *logA, *Aim, *Cre, *Cim, *logdt, *Dskip, *x, *wphi, *wo;
  __nv_bfloat16* out;
  uint4* xs;
  long long* ts;
};

__device__ __forceinline__ uint4 tr_row(const uint4 (&v)[8], int i) {
  uint32_t o[4];
#pragma unroll
  for (int m = 0; m < 4; m++) {
    const uint4 &ra = v[2 * m], &rb = v[2 * m + 1];
    const int k = i >> 1;
    const uint32_t xa = k == 0 ? ra.x : k == 1 ? ra.y : k == 2 ? ra.z : ra.w;
    const uint32_t xb = k == 0 ? rb.x : k == 1 ? rb.y : k == 2 ? rb.z : rb.w;
    o[m] = __byte_perm(xa, xb, (i & 1) ? 0x7632 : 0x5410);
  }
  return make_uint4(o[0], o[1], o[2], o[3]);
}

struct cpx { float r, i; };
__device__ __forceinline__ cpx csq(cpx a) { return {a.r * a.r - a.i * a.i, 2.f * (a.r * a.i)}; }
__device__ __forceinline__ cpx polar(float e, float t) {
  const float m = ex2(e);
  return {m * __cosf(t), m * __sinf(t)};
}

struct KgenRaw { uint32_t la, ai, cr, ci, ldt; };
__device__ __forceinline__ KgenRaw kgen_load(const Params& P, int d, int unit, int lane, int on) {
  const int o = d * 64 + unit * 32 + lane;
  KgenRaw r = {0, 0, 0, 0, 0};
  asm volatile("{\n.reg .pred p;\nsetp.ne.b32 p, %10, 0;\n@p ld.global.nc.u32 %0, [%5];\n@p ld.global.nc.u32 %1, [%6];\n"
               "@p ld.global.nc.u32 %2, [%7];\n@p ld.global.nc.u32 %3, [%8];\n@p ld.global.nc.u16 %4, [%9];\n}\n"
               : "+r"(r.la), "+r"(r.ai), "+r"(r.cr), "+r"(r.ci), "+r"(r.ldt)
               : "l"((const uint32_t*)P.logA + o), "l"((const uint32_t*)P.Aim + o), "l"((const uint32_t*)P.Cre + o),
                 "l"((const uint32_t*)P.Cim + o), "l"(P.logdt + d), "r"(on));
  return r;
}
struct hc { __half2 r, i; };
struct cpx2 { cpx a, b; };
__device__ __forceinline__ cpx2 csq2(const cpx2& v) { return {csq(v.a), csq(v.b)}; }
__device__ __forceinline__ hc toh(const cpx2& v) { return {__floats2half2_rn(v.a.r, v.b.r), __floats2half2_rn(v.a.i, v.b.i)}; }
__device__ __forceinline__ hc hmul(const hc& z, const hc& w) {
  return {__hfma2(z.r, w.r, __hneg2(__hmul2(z.i, w.i))), __hfma2(z.r, w.i, __hmul2(z.i, w.r))};
}
__device__ __forceinline__ hc hmulc(const hc& z, const hc& w) {
  return {__hfma2(z.r, w.r, __hmul2(z.i, w.i)), __hfma2(z.i, w.r, __hneg2(__hmul2(z.r, w.i)))};
}
__device__ __forceinline__ uint32_t hu(__half2 v) { return *(const uint32_t*)&v; }
__device__ __forceinline__ __half2 uh(uint32_t v) { return *(const __half2*)&v; }

struct KgenAddr { uint32_t sa, lb, lm[4]; };
__device__ __forceinline__ KgenAddr kgen_addr(int lane, uint32_t buf) {
  KgenAddr a;
  a.sa = buf + (lane & 7) * 128 + ((((lane >> 3) ^ lane) & 7) << 4);
  const int q = lane >> 4;
  const uint32_t b = buf + ((lane >> 3) & 1) * 1024 + q * 128;
  a.lb = b + (((lane ^ q) & 7) << 4);
  a.lm[0] = b + (q << 4);
  a.lm[1] = b + ((1 ^ q) << 4);
  a.lm[2] = b + (((2 + (lane & 1)) ^ q) << 4);
  a.lm[3] = b + (((4 + (lane & 3)) ^ q) << 4);
  asm volatile("" : "+r"(a.sa), "+r"(a.lb), "+r"(a.lm[0]), "+r"(a.lm[1]), "+r"(a.lm[2]), "+r"(a.lm[3]));
  return a;
}
__device__ __forceinline__ void kgen_unit(const KgenRaw& r, const KgenAddr& ad, uint32_t zero, float (&k)[5][4], float& k2048, float& sc) {
  const float dt = bf_round(expf(bf_lo(r.ldt)));
  const uint32_t ar = pack_bf(ex2(bf_lo(r.la) * 1.4426950408889634f), ex2(bf_hi(r.la) * 1.4426950408889634f));
  const float ca = dt * -1.4426950408889634f, a0 = bf_lo(ar) * ca, a1 = bf_hi(ar) * ca;
  const float f0 = bf_lo(r.ai) * dt, f1 = bf_hi(r.ai) * dt;
  const float r0 = f0 * 20.21267777267071f, r1 = f1 * 20.21267777267071f;
  const uint32_t cm = __vmaxu2(r.cr & 0x7fff7fffu, r.ci & 0x7fff7fffu);
  const uint32_t ex = min(max(__reduce_max_sync(0xffffffffu, max(cm >> 16, cm & 0xffffu)) >> 7, 1u), 253u);
  const float cs = uf((254u - ex) << 23);
  sc = 2.f * dt * uf(ex << 23);
  const cpx2 C = {{bf_lo(r.cr) * cs, bf_lo(r.ci) * -cs}, {bf_hi(r.cr) * cs, bf_hi(r.ci) * -cs}};
  auto put = [&](const hc (&v)[8]) {
    stsm4(ad.sa, hu(v[0].r), hu(v[1].r), hu(v[2].r), hu(v[3].r));
    stsm4(ad.sa + 1024, hu(v[0].i), hu(v[1].i), hu(v[2].i), hu(v[3].i));
    stsm4(ad.sa ^ 64, hu(v[4].r), hu(v[5].r), hu(v[6].r), hu(v[7].r));
    stsm4((ad.sa ^ 64) + 1024, hu(v[4].i), hu(v[5].i), hu(v[6].i), hu(v[7].i));
    __syncwarp();
  };
  auto get = [&](uint32_t (&o)[4][4], uint32_t a) {
#pragma unroll
    for (int i = 0; i < 4; i++) ldsm4(o[i], (a ^ (i << 5)) + i * 256);
  };
  auto at = [](const uint32_t (&o)[4][4], int s) { return hc{uh(o[s >> 1][2 * (s & 1)]), uh(o[s >> 1][2 * (s & 1) + 1])}; };
  uint32_t A[8][4];
  auto tile = [&](int j, const uint32_t (&B)[4][4]) {
    k[j][0] = k[j][1] = k[j][2] = k[j][3] = 0.f;
#pragma unroll
    for (int s = 0; s < 8; s++) mma_h(k[j], A[s], B[s >> 1][2 * (s & 1)], B[s >> 1][2 * (s & 1) + 1]);
  };
  const cpx2 w1 = {polar(a0, f0), polar(a1, f1)};
  const cpx2 w127 = {polar(a0 * 127.f, (r0 - rintf(r0)) * 6.283185307179586f), polar(a1 * 127.f, (r1 - rintf(r1)) * 6.283185307179586f)};
  const cpx2 w2 = csq2(w1), w4 = csq2(w2);
  uint32_t T0[4][4], X[4][4], M[3][4][4];
  {
    hc t[8];
    t[0] = {uh(0x3C003C00u), uh(0u)}; t[1] = toh(w1); t[2] = toh(w2); t[4] = toh(w4);
    t[3] = hmul(t[1], t[2]); t[5] = hmul(t[1], t[4]); t[6] = hmul(t[2], t[4]); t[7] = hmul(t[3], t[4]);
    put(t); get(T0, ad.lb);
  }
  const cpx2 w8 = csq2(w4), w16 = csq2(w8), w32 = csq2(w16), w64 = csq2(w32);
  {
    const hc m8 = toh(w8), m16 = toh(w16), m32 = toh(w32);
    hc a[8];
    a[0] = toh(C); a[1] = hmulc(a[0], m8);
    a[2] = hmulc(a[0], m16); a[3] = hmulc(a[1], m16);
#pragma unroll
    for (int i = 0; i < 4; i++) a[4 + i] = hmulc(a[i], m32);
    put(a); get(X, ad.lb);
  }
    const cpx2 w128 = {{w127.a.r * w1.a.r - w127.a.i * w1.a.i, w127.a.r * w1.a.i + w127.a.i * w1.a.r},
                     {w127.b.r * w1.b.r - w127.b.i * w1.b.i, w127.b.r * w1.b.i + w127.b.i * w1.b.r}};
  const cpx2 w256 = csq2(w128), w512 = csq2(w256);
  const hc m128 = toh(w128), m256 = toh(w256), m512 = toh(w512);
  {
    const hc m254 = toh(csq2(w127)), m127 = toh(w127);
    hc m[8];
    m[0] = toh(w64); m[1] = m128; m[2] = m256; m[3] = hmul(m127, m256);
    m[4] = m512; m[5] = hmul(m127, m512); m[6] = hmul(m[4], m254); m[7] = hmul(m[5], m254);
    put(m);
    get(M[0], ad.lm[0]);
#pragma unroll
    for (int s = 0; s < 8; s++) {
      const hc z = at(X, s), y = hmulc(z, at(M[0], s));
      A[s][0] = hu(z.r) + zero; A[s][1] = hu(y.r); A[s][2] = hu(z.i) + zero; A[s][3] = hu(y.i);
    }
#pragma unroll
    for (int i = 0; i < 3; i++) get(M[i], ad.lm[i + 1]);
  }
  tile(0, T0);
  const cpx2 w1024 = csq2(w512), we = csq2(w1024);
  {
    hc t[8];
    t[0] = toh(w1024); t[1] = hmul(t[0], m128);
    t[2] = hmul(t[0], m256); t[3] = hmul(t[1], m256);
#pragma unroll
    for (int i = 0; i < 4; i++) t[4 + i] = hmul(t[i], m512);
    put(t); get(X, ad.lb);
  }
  k2048 = (C.a.r * we.a.r + C.a.i * we.a.i + C.b.r * we.b.r + C.b.i * we.b.i) * sc;
#pragma unroll
  for (int j = 1; j < 5; j++) k[j][0] = k[j][1] = k[j][2] = k[j][3] = 0.f;
#pragma unroll
  for (int s = 0; s < 8; s++) {
#pragma unroll
    for (int j = 0; j < 3; j++) {
      const hc y = hmul(at(T0, s), at(M[j], s));
      mma_h(k[1 + j], A[s], hu(y.r), hu(y.i));
    }
    mma_h(k[4], A[s], X[s >> 1][2 * (s & 1)], X[s >> 1][2 * (s & 1) + 1]);
  }
}

__device__ __forceinline__ void build_tables(uint32_t tb, int lane, float (&k)[5][4], float k2048) {
  const int g = lane >> 2, c = lane & 3;
  const uint32_t kc = tb + T_KC + 16;
  {
    const uint32_t a0 = kc + 16 * g + 4 * c, a2 = kc + 2 * (256 + 4 * g + c);
    const uint32_t a3 = kc + 2 * (384 + 2 * g + 64 * (c & 1) + (c >> 1)), a4 = kc + 2 * (512 + g + 32 * c);
#pragma unroll
    for (int r = 0; r < 2; r++) {
      sts32(a0 + 128 * r, pack_bf(k[0][2 * r], k[0][2 * r + 1]));
      sts32(a0 + 128 * r + 256, pack_bf(k[1][2 * r], k[1][2 * r + 1]));
      const uint32_t w2 = pack_bf(k[2][2 * r], k[2][2 * r + 1]);
      const uint32_t w3 = pack_bf(k[3][2 * r], k[3][2 * r + 1]);
      const uint32_t w4 = pack_bf(k[4][2 * r], k[4][2 * r + 1]);
      sts16(a2 + 64 * r, w2); sts16(a2 + 64 * r + 128, w2 >> 16);
      sts16(a3 + 32 * r, w3); sts16(a3 + 32 * r + 64, w3 >> 16);
      sts16(a4 + 16 * r, w4); sts16(a4 + 16 * r + 32, w4 >> 16);
    }
  }
  if (lane == 0) { sts16(kc + 2 * 640, pack_bf(k2048, 0.f)); sts32(kc - 4, 0); }
  __syncwarp();
  const uint32_t td = tb + T_D + 32;
#pragma unroll
  for (int hf = 0; hf < 2; hf++) {
    const uint2 v = lds64(kc + 256 * hf + 8 * lane);
    const uint32_t pv = lds32(kc + 256 * hf + 8 * lane - 4);
    sts128(td + 512 * hf + 16 * lane, __byte_perm(v.x, pv, 0x7610), __byte_perm(v.x, v.x, 0x1032), __byte_perm(v.y, v.x, 0x7610),
           __byte_perm(v.y, v.y, 0x1032));
  }
#pragma unroll
  for (int hf = 0; hf < 2; hf++) {
    const uint32_t v = lds32(kc + 512 + 128 * hf + 4 * lane), nx = lds32(kc + 516 + 128 * hf + 4 * lane);
    uint32_t w0 = __byte_perm(v, v, 0x1010);
    const uint32_t w1 = w0;
    if (hf == 0) { const uint32_t pv = lds32(kc + 508); if (lane == 0) w0 = __byte_perm(v, pv, 0x7610); }
    sts128(td + 1024 + 512 * hf + 16 * lane, w0, w1, __byte_perm(v, v, 0x1032), __byte_perm(nx, v, 0x7610));
  }
  {
    const uint32_t kk = lds16(kc + 2 * 384);
    const uint32_t w = lane < 3 ? (kk | (kk << 16)) : (lane == 3 ? (kk << 16) : 0u);
    if (lane < 24) sts32(td + 4 * (lane < 16 ? 512 + lane : lane - 24), w);
    const uint32_t lo_ = lds16(kc + 2 * 511), le_ = lds16(kc + 2 * 512);
    const uint32_t ja = tb + T_5 + (lane < 16 ? 4 * lane : 256 + 4 * lane);
    sts32(ja, lane == 16 ? (le_ << 16) : 0u);
    sts32(ja + 384, lane == 16 ? (lo_ << 16) : 0u);
    sts32(tb + (lane < 16 ? T_7 : T_9 - 64) + 4 * lane, 0u);
  }
#pragma unroll
  for (int s = 0; s < 2; s++) {
    const uint32_t b = kc + 2 * (s ? 512 : 384) + 8 * lane;
    const uint2 v = lds64(b);
    uint32_t em = lds16(b - 2), e0 = v.x;
    const uint32_t e4 = lds16(b + 8);
    if (lane == 0) { em = 0; e0 = 0; }
    sts64(tb + (s ? T_7 : T_3) + 64 + 8 * lane, __byte_perm(v.x, em, 0x5432), __byte_perm(v.y, v.x, 0x7632));
    sts64(tb + (s ? T_9 : T_5) + 64 + 8 * lane, __byte_perm(v.y, e0, 0x5410), __byte_perm(e4, v.y, 0x5410));
  }
  __syncwarp();
}

__device__ __forceinline__ uint32_t box2w(int lo, int n, int o) {
  return ((unsigned)(o - lo) < (unsigned)n ? 0x3F80u : 0u) | ((unsigned)(o + 1 - lo) < (unsigned)n ? 0x3F800000u : 0u);
}

__device__ __forceinline__ void conv_channel(uint32_t ub, uint32_t tb, int lane, uint4* ydst) {
  const int g = lane >> 2, c = lane & 3, x = g - 2 * c;
  const int mi = lane >> 3;
  const uint32_t qa = ub + U_PAD + 16 * (lane & 7) + ((mi == 0 || mi == 3) ? U_ODD : 0) - (mi == 0 ? 16 : 0);
  const uint32_t hb = ub + U_PAD + (mi & 1) * U_ODD + 16 * ((lane >> 4) + (lane & 7)) - 16;
  const uint32_t kv = lds16(tb + T_KC + 16 + 2 * 512);
  const int oh = c < 2 ? 8 + 2 * c : 2 * c - 8, og = c < 3 ? 2 * c : -10;
  uint32_t bx[4] = {box2w(g - 4, 9, 2 * c), box2w(g - 3, 7, 2 * c), box2w(g - 4, 9, oh), box2w(g - 3, 7, oh)};
  uint32_t by[4] = {box2w(g - 10, 5, 2 * c - 8), box2w(g - 5, 3, 2 * c - 8), box2w(g - 10, 5, og), box2w(g - 5, 3, og)};
  uint32_t lb0 = ((unsigned)(x + 5) < 2u ? kv : 0u) | ((unsigned)(x + 4) < 2u ? kv << 16 : 0u);
  uint32_t lb1 = ((unsigned)(x - 3) < 2u ? kv : 0u) | ((unsigned)(x - 4) < 2u ? kv << 16 : 0u);
  const int q0 = g - 1, q1 = c < 3 ? g : g - 2;
  uint32_t y0a = ub + U_PAD + (q0 & 1) * U_ODD + 16 * (q0 >> 1) + 4 * c;
  uint32_t y1a = ub + U_PAD + (q1 & 1) * U_ODD + 16 * (q1 >> 1) + 4 * c;
#pragma unroll
  for (int i = 0; i < 4; i++) asm volatile("" : "+r"(bx[i]), "+r"(by[i]));
  asm volatile("" : "+r"(lb0), "+r"(lb1), "+r"(y0a), "+r"(y1a));
  mbar_wait(BAR(MB_UFULL));
  mbar_spin(BAR(MB_EMPTY + 15));
  TS(36);
  float acc[16][4];
  {
    uint32_t z09[8], z07[8], zm9[8], zm7[8];
#pragma unroll
    for (int i = 0; i < 8; i++) {
      uint32_t h[4];
      ldsm4(h, hb + 128 * i);
      float y0, y1, y2, y3, w0, w1, w2, w3;
      mma0(y0, y1, y2, y3, bx[0], bx[1], bx[2], bx[3], h[2], c < 2 ? h[3] : h[1]);
      mma0(w0, w1, w2, w3, bx[0], bx[1], bx[2], bx[3], h[1], c < 2 ? h[2] : h[0]);
      z09[i] = pack_bf(y0, y1); z07[i] = pack_bf(y2, y3);
      zm9[i] = pack_bf(w0, w1); zm7[i] = pack_bf(w2, w3);
    }
  uint32_t f3[3][4][4];
  {
    const uint32_t fa = tb + T_7 + 4 * (16 + x);
#pragma unroll
    for (int tt = 0; tt < 3; tt++)
#pragma unroll
      for (int D = 0; D < 4; D++) {
        const uint32_t a = fa + (tt == 0 ? 316 : (tt == 1 ? 320 : 0)) + 64 * D;
        f3[tt][D][0] = lds32(a); f3[tt][D][1] = lds32(a + 32); f3[tt][D][2] = lds32(a - 32); f3[tt][D][3] = lds32(a);
      }
  }
    SPLIT();
    nb_sync(NB_GATE, 256);
    SPLIT();
    float a[4][2][4];
#pragma unroll
    for (int kap = 0; kap < 4; kap++)
#pragma unroll
      for (int sg = 0; sg < 2; sg++)
#pragma unroll
        for (int bk = 3; bk >= kap; bk--) {
          const uint32_t(&q0_)[4] = f3[sg ? 2 : 0][bk - kap];
          const uint32_t(&q1_)[4] = f3[sg ? 2 : 1][bk - kap];
          float(&a0)[4] = a[bk][0];
          float(&a1)[4] = a[bk][1];
          if (sg == 0 && kap == 0) {
            mma0(a0[0], a0[1], a0[2], a0[3], q0_[0], q0_[1], q0_[2], q0_[3], z09[0], z09[1]);
            mma0(a1[0], a1[1], a1[2], a1[3], q1_[0], q1_[1], q1_[2], q1_[3], zm9[0], zm9[1]);
          } else {
            mma(a0[0], a0[1], a0[2], a0[3], q0_[0], q0_[1], q0_[2], q0_[3], sg ? zm7[2 * kap] : z09[2 * kap], sg ? zm7[2 * kap + 1] : z09[2 * kap + 1]);
            mma(a1[0], a1[1], a1[2], a1[3], q1_[0], q1_[1], q1_[2], q1_[3], sg ? z07[2 * kap] : zm9[2 * kap], sg ? z07[2 * kap + 1] : zm9[2 * kap + 1]);
          }
        }
    SPLIT();
#pragma unroll
    for (int i = 0; i < 8; i++) {
      uint32_t h[4];
      ldsm4(h, qa + 128 * i);
      const float ci[4] = {a[i >> 1][0][2 * (i & 1)], a[i >> 1][0][2 * (i & 1) + 1], a[i >> 1][1][2 * (i & 1)], a[i >> 1][1][2 * (i & 1) + 1]};
      mmac(acc[8 + i], h[0], h[1], h[2], h[3], lb0, lb1, ci);
    }
  }
  TS(44);
  {
    uint2 a5[10], a3[10];
    const uint32_t aa = tb + T_5 + 4 * (8 + 2 * g - 2 * c);
#pragma unroll
    for (int m = 0; m < 10; m++) { a5[m] = lds64(aa + 32 * m); a3[m] = lds64(aa + 384 + 32 * m); }
    uint32_t x5[12][2], x3[12][2];
    auto ygen = [&](int kap) {
#pragma unroll
      for (int hh = 0; hh < 2; hh++) {
        float y0, y1, y2, y3;
        mma0(y0, y1, y2, y3, by[0], by[1], by[2], by[3], lds32(y0a + 128 * kap + 64 * hh), lds32(y1a + 128 * kap + 64 * hh));
        x5[kap][hh] = pack_bf(y0, y1);
        x3[kap][hh] = pack_bf(y2, y3);
      }
    };
    ygen(11); ygen(10); ygen(9); ygen(8);
#pragma unroll
    for (int kap = 11; kap >= 0; kap--) {
      if (kap >= 4) ygen(kap - 4);
#pragma unroll
      for (int sg = 0; sg < 2; sg++)
#pragma unroll
        for (int i = 4; i >= 0; i--) {
          const int be = kap + 4 + i;
          if (be <= 15) {
            const uint2 &hi = sg ? a3[2 * i + 1] : a5[2 * i + 1], &lo = sg ? a3[2 * i] : a5[2 * i];
            const uint32_t b0 = sg ? x3[kap][0] : x5[kap][0], b1 = sg ? x3[kap][1] : x5[kap][1];
            if (be < 8 && i == 0 && sg == 0) mma0(acc[be][0], acc[be][1], acc[be][2], acc[be][3], hi.x, hi.y, lo.x, lo.y, b0, b1);
            else mma(acc[be][0], acc[be][1], acc[be][2], acc[be][3], hi.x, hi.y, lo.x, lo.y, b0, b1);
          }
        }
    }
  }
  TS(45);
  {
    const uint32_t st = tb + T_ST + lane * 8;
#pragma unroll
    for (int be = 4; be < 12; be++) sts64(st + 256 * be, pack_bf(acc[be][0], acc[be][1]), pack_bf(acc[be][2], acc[be][3]));
    SPLIT();
    uint32_t F[66], qd[8][4];
    const uint32_t fa = tb + T_D + 32 + 4 * x;
#pragma unroll
    for (int i = 0; i < 32; i++) {
      const int s = 120 - (i >> 2) - 8 * (i & 3);
      uint32_t(&q)[4] = qd[i & 7];
      ldsm4(q, qa + 16 * s);
      const int m = 16 * (i & 3) + 2 * (i >> 2);
      F[m] = lds32(fa + 32 * m); F[m + 1] = lds32(fa + 32 * m + 32);
#pragma unroll
      for (int be = 15; be >= 12; be--) {
        const int de = 8 * be - s;
        float(&a)[4] = (be >= 14 && !(i & 1)) ? acc[be - 4] : acc[be];
        if (de >= 0 && be >= 14 && i == 2 * (15 - be)) mma0(a[0], a[1], a[2], a[3], q[0], q[1], q[2], q[3], F[2 * de + 1], F[2 * de]);
        else if (de >= 0) mma(a[0], a[1], a[2], a[3], q[0], q[1], q[2], q[3], F[2 * de + 1], F[2 * de]);
      }
    }
#pragma unroll
    for (int i = 0; i < 8; i++) acc[14 + (i >> 2)][i & 3] += acc[10 + (i >> 2)][i & 3];
    F[64] = lds32(fa + 32 * 64); F[65] = lds32(fa + 32 * 65);
#pragma unroll
    for (int i = 0; i < 6; i++) ldsm4(qd[i], qa + 128 * 11 - 16 * i);
    uint2 sv = lds64(st + 256 * 11);
    float ci[4] = {bf_lo(sv.x), bf_hi(sv.x), bf_lo(sv.y), bf_hi(sv.y)};
    float T[5][4];
#pragma unroll
    for (int i = 0; i < 16; i++) T[i >> 2][i & 3] = acc[12 + (i >> 2)][i & 3];
    nb_sync(NB_YZ, 160);
    TS(46);
    uint32_t held[2];
#pragma unroll
    for (int be = 11; be >= 0; be--) {
      if (be & 1) SPLITN(be);
      const uint32_t qp = qa + 128 * be;
#pragma unroll
      for (int k = 4; k >= 1; k--) mmac(T[k], qd[0][0], qd[0][1], qd[0][2], qd[0][3], F[16 * k + 1], F[16 * k], T[k - 1]);
      if (be >= 4) mmac(T[0], qd[0][0], qd[0][1], qd[0][2], qd[0][3], F[1], F[0], ci);
      else mma0(T[0][0], T[0][1], T[0][2], T[0][3], qd[0][0], qd[0][1], qd[0][2], qd[0][3], F[1], F[0]);
      ldsm4(qd[6], qp - 16 * 6);
      ldsm4(qd[7], qp - 16 * 7);
      if (be > 4) sv = lds64(st + 256 * (be - 1));
#pragma unroll
      for (int i = 1; i < 8; i++) {
#pragma unroll
        for (int k = 3; k >= 0; k--)
          mma(T[k][0], T[k][1], T[k][2], T[k][3], qd[i][0], qd[i][1], qd[i][2], qd[i][3], F[16 * k + 2 * i + 1], F[16 * k + 2 * i]);
        if (i < 7 && be > 0) ldsm4(qd[i - 1], qp - 128 - 16 * (i - 1));
        if (i == 2) {
          const uint32_t w0 = pack_bf(T[4][0], T[4][1]), w1 = pack_bf(T[4][2], T[4][3]);
          if (be & 1) { held[0] = w0; held[1] = w1; }
          else st_x(ydst + (be + 4) * 16, nz(w0), w1, held[0], held[1]);
          if ((be & 3) == 3 && be < 11) nb_arrive(NB_Y + 2 + (be >> 2), 160);
        }
        if (i == 4 && be > 4) { ci[0] = bf_lo(sv.x); ci[1] = bf_hi(sv.x); ci[2] = bf_lo(sv.y); ci[3] = bf_hi(sv.y); }
      }
    }
    nb_arrive(NB_Y + 1, 160);
#pragma unroll
    for (int B = 1; B >= 0; B--)
      st_x(ydst + B * 32, nz(pack_bf(T[2 * B][0], T[2 * B][1])), pack_bf(T[2 * B][2], T[2 * B][3]),
           pack_bf(T[2 * B + 1][0], T[2 * B + 1][1]), pack_bf(T[2 * B + 1][2], T[2 * B + 1][3]));
  }
}

__device__ __forceinline__ void dual_exp(const uint32_t* w, uint32_t* e) {
  const float L = 1.44268798828125f;
  uint32_t mx = bmax2(bmax2(w[0], w[1]), bmax2(w[2], w[3]));
  uint32_t mn = bmin2(bmin2(w[0], w[1]), bmin2(w[2], w[3]));
  mx = bmax2(mx, __shfl_xor_sync(0xffffffffu, mx, 1));
  mn = bmin2(mn, __shfl_xor_sync(0xffffffffu, mn, 1));
  mx = bmax2(mx, __shfl_xor_sync(0xffffffffu, mx, 2));
  mn = bmin2(mn, __shfl_xor_sync(0xffffffffu, mn, 2));
  const float mx0 = bf_lo(mx) * -L, mx1 = bf_hi(mx) * -L, mn0 = bf_lo(mn) * L, mn1 = bf_hi(mn) * L;
#pragma unroll
  for (int i = 0; i < 2; i++) {
    const float a0 = bf_lo(w[2 * i]), a1 = bf_hi(w[2 * i]), b0 = bf_lo(w[2 * i + 1]), b1 = bf_hi(w[2 * i + 1]);
    e[2 * i] = pack_bf(ex2(fmaf(a0, L, mx0)), ex2(fmaf(b0, L, mx0)));
    e[2 * i + 1] = pack_bf(ex2(fmaf(a1, L, mx1)), ex2(fmaf(b1, L, mx1)));
    e[4 + 2 * i] = pack_bf(ex2(fmaf(a0, -L, mn0)), ex2(fmaf(b0, -L, mn0)));
    e[5 + 2 * i] = pack_bf(ex2(fmaf(a1, -L, mn1)), ex2(fmaf(b1, -L, mn1)));
  }
}
__device__ __forceinline__ void normalise(uint32_t* e, const float (&s)[4]) {
  const uint32_t r = pack_bf(rcp(s[0]), rcp(s[2]));
  const __nv_bfloat162 rr = *(const __nv_bfloat162*)&r;
#pragma unroll
  for (int i = 0; i < 4; i++) {
    const __nv_bfloat162 v = __hmul2(*(const __nv_bfloat162*)&e[i], (i & 1) ? __high2bfloat162(rr) : __low2bfloat162(rr));
    e[i] = *(const uint32_t*)&v;
  }
}
__host__ __device__ constexpr uint64_t qdesc(uint32_t addr) { return mkdesc(addr, 128, 256, 0); }

__global__ void __launch_bounds__(NTHREADS, 1)
fused_kernel(const Params P, const __grid_constant__ CUtensorMap mx, const __grid_constant__ CUtensorMap mw,
             const __grid_constant__ CUtensorMap mo, const __grid_constant__ CUtensorMap mu,
             const __grid_constant__ CUtensorMap mout) {
  constexpr uint32_t sb = SB;
  const int tid = threadIdx.x, lane = tid & 31;
  const int warp = __shfl_sync(0xffffffffu, tid >> 5, 0);
  const int b = blockIdx.x, oct = b >> 3, i8 = b & 7;
  const int rt = (((oct & 4) ? ~oct : oct) & 3) * 2 + (i8 >> 2);
  const int hp = (oct >> 2) * 4 + (i8 & 3);

  const int wg = warp >> 2, w = warp & 3;
  const int d = b * 4 + ((tid >> 5) & 3);
  const KgenRaw raw = kgen_load(P, d, (tid >> 7) & 1, lane, (tid + 128) & 256);
  const uint32_t tb = sb + OFF_T + w * T_CH;
  if (warp >= 12) {
    asm volatile("setmaxnreg.dec.sync.aligned.u32 32;");
    if (warp == 12) {
      if (lane == 0) {
#pragma unroll
        for (int i = 0; i < 9; i++) mbar_init(BAR(i), 1);
        asm volatile("fence.mbarrier_init.release.cluster;" ::: "memory");
      }
      __syncwarp();
      if (lane < 9) mbar_expect(BAR(0) + 8 * lane, lane == 0 ? 16384 : 28672);
      __syncwarp();
      nb_arrive(NB_PROD, 384);
#pragma unroll 1
      for (int kb = 0; kb < 8; kb++) {
        if (kb == U_AT) e_tma4d(sb + OFF_STG0, &mu, BAR(MB_URAW), i8 * 64, oct * 2);
        e_tma3d(sb + OFF_W + kb * 12288, &mw, BAR(MB_FULL) + 8 * kb, hp * 32, kb * 64, 0);
        if (kb < 5) e_tma2d(sb + OFF_X + (kb < 2 ? kb + 3 : kb - 2) * 16384, &mx, BAR(MB_FULL) + 8 * kb, kb * 64, rt * 256);
      }
      if (smem_u32(smem_raw) != SB) __trap();
      if (lane == 0) TS1(54);
      nb_sync(NB_GATE + 1, 64);
      e_prefetch(P.x + (size_t)(rt * 256 + 128 + hp * 8) * 512, 8192);
      uint32_t slot = sb + OFF_X + 3 * 16384;
#pragma unroll 1
      for (int n = 0; n < 11; n++) {
        mbar_spin(BAR(MB_EMPTY) + 8 * n);
        const int m = n + 5;
        e_tma2d(slot, &mx, BAR(MB_FULL) + 8 * m, (m & 7) * 64, rt * 256 + (m >> 3) * 128);
        slot = slot == sb + OFF_X + 4 * 16384 ? sb + OFF_X : slot + 16384;
        if (n == 7) {
          e_prefetch(P.wo + (size_t)b * 2048, 4096);
          asm volatile("prefetch.tensormap [%0];" ::"l"(&mo) : "memory");
          asm volatile("prefetch.tensormap [%0];" ::"l"(&mout) : "memory");
        }
      }
#pragma unroll 1
      for (int i = 0; i < 8; i++) {
        mbar_wait(BAR(MB_EMPTY + 10) + 8 * ((0x54332222u >> (4 * i)) & 7));
        const int w0 = (0x54736210u >> (4 * i)) & 7;
        e_tma3d(sb + OFF_W + w0 * 16384, &mo, BAR(MB_WO), 0, w0 * 64, (hp & 3) * 2);
      }
    } else {
      if (warp == 13) {
        if (lane == 0) {
#pragma unroll
          for (int i = 9; i < 40; i++) mbar_init(BAR(i), i < MB_EMPTY ? 1 : 4);
          asm volatile("fence.mbarrier_init.release.cluster;" ::: "memory");
        }
        __syncwarp();
        if (lane < 14 && lane != 9) mbar_expect(BAR(MB_FULL + 8) + 8 * lane, lane == 8 ? 131072 : (lane == 10 ? 8192 : (lane == 13 ? 24576 : 16384)));
        nb_arrive(NB_GATE + 1, 64);
      } else if (warp == 14) {
        asm volatile("prefetch.tensormap [%0];" ::"l"(&mw) : "memory");
        asm volatile("prefetch.tensormap [%0];" ::"l"(&mx) : "memory");
        asm volatile("prefetch.tensormap [%0];" ::"l"(&mu) : "memory");
        e_prefetch(P.x + (size_t)(rt * 256 + hp * 8) * 512, 8192);
      }
      nb_sync(NB_PROD, 384);
      if (warp == 15) {
        const uint4 v0 = __ldg((const uint4*)P.wphi + hp * 64 + lane), v1 = __ldg((const uint4*)P.wphi + hp * 64 + 32 + lane);
        sts128(sb + OFF_PHI + (lane & 1) * 256 + (lane >> 1) * 16, v0.x, v0.y, v0.z, v0.w);
        sts128(sb + OFF_PHI + 512 + (lane & 1) * 256 + (lane >> 1) * 16, v1.x, v1.y, v1.z, v1.w);
        const uint32_t one = (((lane >> 3) ^ (lane >> 4)) & 1) ? 0u : ((lane & 1) ? 0x3F800000u : 0x3F80u);
        const int q = (lane >> 1) & 3;
        sts128(sb + OFF_EYE + lane * 16, q == 0 ? one : 0u, q == 1 ? one : 0u, q == 2 ? one : 0u, q == 3 ? one : 0u);
        sts64(sb + OFF_ONE + lane * 8, 0x3F803F80u, 0x3F803F80u);
        asm volatile("fence.proxy.async.shared::cta;" ::: "memory");
        nb_arrive(NB_KREAD, 160);
      }
      uint32_t* cnt = (uint32_t*)(P.xs + X_CNT) + (warp == 13 ? i8 : (warp == 14 ? 8 + rt : 16 + oct)) * 32;
      const unsigned target = (ld_x32(cnt) & ~15u) + 16;
      if (warp != 14) {
        if (warp == 15) mbar_wait(BAR(MB_EMPTY + ZERO_STEP));
        uint4* pz = P.xs + (warp == 13 ? X_PART + (hp * 8 + rt) * 144 : X_Y + b * 1024) + lane;
#pragma unroll 1
        for (int i = (warp == 13 ? 144 : 1024) - lane; i > 0; i -= 32, pz += 32) st_x(pz, 0, 0, 0, 0);
      }
      if (warp == 15) __syncwarp();
      else nb_sync(warp == 13 ? NB_INIT : NB_ODONE, warp == 13 ? 160 : 288);
      if (lane == 0) asm volatile("red.release.gpu.global.add.u32 [%0], %1;" ::"l"(cnt), "r"(warp == 15 ? 2 : 1) : "memory");
      if (lane == 0) TS1(warp == 13 ? 50 : (warp == 14 ? 57 : 53));
      __syncwarp();
      if (warp == 14) nb_arrive(NB_GATE + 1, 160);
      asm volatile("fence.proxy.async.shared::cta;" ::: "memory");
      if (warp == 13) cnt += ((lane & 1 ? b >> 4 : i8 ^ (lane & 4)) - i8) * 32;
#pragma unroll 1
      for (int i = 0; i < SPIN_MAX; i++) {
        unsigned v;
        asm volatile("ld.acquire.gpu.global.u32 %0, [%1];" : "=r"(v) : "l"(cnt) : "memory");
        if (__all_sync(0xffffffffu, (int)(v - target) >= 0)) break;
      }
      if (lane == 0) TS1(warp == 13 ? 51 : (warp == 14 ? 58 : 55));
      if (warp == 15) { nb_arrive(NB_YZ, 160); return; }
      asm volatile("fence.proxy.async.global;" ::: "memory");
      if (warp == 13) {
        mbar_wait(BAR(MB_EMPTY + 11));
        e_expect(BAR(MB_UFULL), 4 * U_CH);
        e_bulk(sb + OFF_U, P.xs + X_UT + b * (U_CH / 4), 4 * U_CH, BAR(MB_UFULL));
      } else {
        const uint4* src = P.xs + X_O + (rt * 4 + (hp >> 2)) * 4096;
        e_bulk(sb + OFF_X + 32768 + 57344, src + 3584, 8192, BAR(MB_O));
        e_bulk(sb + OFF_X + 32768, src, 16384, BAR(MB_O + 1));
        e_bulk(sb + OFF_X + 49152, src + 1024, 16384, BAR(MB_O + 2));
        e_bulk(sb + OFF_STG0, src + 3200, 6144, BAR(MB_O + 3));
        nb_sync(NB_BDONE, 288);
        asm volatile("fence.proxy.async.shared::cta;" ::: "memory");
        e_bulk(sb + OFF_U, src + 2048, 18432, BAR(MB_O + 3));
      }
    }
    return;
  }

  asm volatile("setmaxnreg.inc.sync.aligned.u32 160;");
  const int t = tid & 127;
  const int g = lane >> 2, c = lane & 3;
  const uint32_t kp = ((tb + 127) & ~127u) + (wg & 1) * 2048;
  const KgenAddr kad = kgen_addr(lane, kp);
  if (wg) nb_sync(NB_PROD, 384);
  float k[5][4], k2048, ksc;
  if (wg) {
    kgen_unit(raw, kad, blockIdx.y, k, k2048, ksc);
    TS(40 + wg);
    if ((fu(k[0][0]) & fu(k[1][0]) & fu(k[2][0]) & fu(k[3][0]) & fu(k[4][0])) == 0xffffffffu) sts32(kp, 0);
  }
  if (wg) nb_arrive(0, 384);
  if (wg) {
    if (wg == 1) {
      uint32_t h[10];
#pragma unroll
      for (int j = 0; j < 10; j++) h[j] = hu(__floats2half2_rn(k[j >> 1][2 * (j & 1)], k[j >> 1][2 * (j & 1) + 1]));
      sts128(kp + lane * 16, h[0], h[1], h[2], h[3]);
      sts128(kp + 512 + lane * 16, h[4], h[5], h[6], h[7]);
      sts128(kp + 1024 + lane * 16, h[8], h[9], fu(k2048), fu(ksc));
      nb_arrive(NB_PREP, 256);
    }
  } else {
    nb_sync(NB_KREAD, 160);
    nb_sync(0, 384);
  }
  if (wg == 1) {
    mbar_wait(BAR(MB_URAW));
    TS(48);
    uint4* dst = P.xs + X_UT + (i8 * 64 + g) * (U_CH / 16) + (w & 1) * (U_ODD / 16) + U_PAD / 16 + oct * 8 + (w >> 1) * 4 + c;
    const int ln = ((lane >> 1) & 3) + 4 * (lane & 1);
    uint32_t r[8][4];
#pragma unroll
    for (int i = 0; i < 8; i++) ldsm4t(r[i], sb + OFF_STG0 + w * 4096 + ((lane >> 3) * 8 + ln) * 128 + ((i ^ ln) << 4));
#pragma unroll
    for (int i = 0; i < 8; i++) dst[i * (U_CH / 2)] = make_uint4(r[i][0], r[i][1], r[i][2], r[i][3]);
    nb_arrive(NB_INIT, 160);
    if (lane == 0) mbar_arrive(BAR(MB_AUX));
  }
  {
    if (wg == 2) {
#pragma unroll
      for (int j = 0; j < 5; j++) { k[j][0] *= ksc; k[j][1] *= ksc; k[j][2] *= ksc; k[j][3] *= ksc; }
      const unsigned short dsk = __ldg((const unsigned short*)P.Dskip + d);
      nb_sync(NB_PREP, 256);
      {
        const uint32_t src = kp + 2048 + lane * 16;
        const uint4 v0 = lds128(src), v1 = lds128(src + 512), v2 = lds128(src + 1024);
        const uint32_t h[10] = {v0.x, v0.y, v0.z, v0.w, v1.x, v1.y, v1.z, v1.w, v2.x, v2.y};
#pragma unroll
        for (int j = 0; j < 10; j++) {
          const float2 f = __half22float2(*(const __half2*)&h[j]);
          k[j >> 1][2 * (j & 1)] = fmaf(f.x, uf(v2.w), k[j >> 1][2 * (j & 1)]);
          k[j >> 1][2 * (j & 1) + 1] = fmaf(f.y, uf(v2.w), k[j >> 1][2 * (j & 1) + 1]);
        }
        k2048 += uf(v2.z);
      }
#pragma unroll
      for (int o2 = 16; o2; o2 >>= 1) k2048 += __shfl_xor_sync(0xffffffffu, k2048, o2);
      if (lane == 0) k[0][0] += bf_lo(dsk);
      __syncwarp();
      TS(34);
      build_tables(tb, lane, k, k2048);
      TS(35);
      uint4* const g_y = P.xs + X_Y;
      conv_channel(sb + OFF_U + w * U_CH, tb, lane, g_y + (size_t)d * 256 + lane);
      nb_arrive(NB_BDONE, 288);
      nb_arrive(NB_Y, 160);
      TS(37);
      if (w == 0) TSDUMP(32);
      return;
    }
    if (wg == 1) {
      mbar_wait(BAR(MB_EMPTY + 4));
      mbar_spin(BAR(MB_EMPTY + 6));
    }
    TS(wg * 16 + 1);
  }

  float acc[2][48];
  {
    uint32_t fb = BAR(MB_FULL) + 64 * wg;
    uint32_t da = (uint32_t)mkdesc(sb + OFF_X, 16, 0, 0) + (wg ? 1024 : 3072), db = (uint32_t)mkdesc(sb + OFF_W, 4096, 0, 0);
    constexpr uint64_t ha = mkdesc(0, 0, 1024, 1), hb = mkdesc(0, 0, 512, 2);
    mbar_spin(fb);
    TS(wg * 16 + 2);
#pragma unroll 1
    for (int kb = 0; kb < 8; kb++) {
      WG_FENCE();
#pragma unroll
      for (int k = 0; k < 4; k++) {
        wgmma_ss_n96(acc[0], ha | (da + 2 * k), hb | (db + 64 * k), k ? 1 : kb);
        wgmma_ss_n96(acc[1], ha | (da + 2 * k + 512), hb | (db + 64 * k), k ? 1 : kb);
      }
      WG_COMMIT();
      if (kb < 7) mbar_spin(fb + 8);
      WG_WAIT(1);
      if (kb > 0) e_arrive(fb + 8 * (MB_EMPTY - MB_FULL - 1));
      fb += 8; db += 768;
      da = da == (uint32_t)mkdesc(sb + OFF_X + 65536, 16, 0, 0) ? da - 4096 : da + 1024;
    }
    WG_WAIT(0);
    e_arrive(fb + 8 * (MB_EMPTY - MB_FULL - 1));
    SPLIT();
  }
  TS(wg * 16 + 3);

  constexpr uint32_t stg0 = sb + OFF_STG0, stg1 = sb + OFF_X + 32768;
  uint4* const g_part = P.xs + X_PART;
  uint4* const g_o = P.xs + X_O;
  constexpr uint32_t kvs = stg0;
  auto pack8 = [](const float* a) { return make_uint4(pack_bf(a[0], a[1]), pack_bf(a[2], a[3]), pack_bf(a[4], a[5]), pack_bf(a[6], a[7])); };
  auto stage_k = [&](auto nt, const uint4* af, const uint4* vp, uint32_t sl, uint32_t free_bar) {
    constexpr int NU = 2 * decltype(nt)::value;
    float p[NU][8], rs[2 * NU][4];
    uint32_t ek[8 * NU];
    WG_FENCE();
#pragma unroll
    for (int u = 0; u < NU; u++) wgmma_rs_n16(p[u], af[u], qdesc(sb + OFF_PHI + (u & 1) * 512), 0);
    WG_COMMIT();
    WG_WAIT(0);
#pragma unroll
    for (int u = 0; u < NU; u++) {
      const uint32_t pw[4] = {pack_bf(p[u][0], p[u][2]), pack_bf(p[u][1], p[u][3]), pack_bf(p[u][4], p[u][6]), pack_bf(p[u][5], p[u][7])};
      dual_exp(pw, ek + 8 * u);
    }
    TS(wg * 16 + 12);
    if (NU == 2 && wg && (ek[0] & ek[15]) != 0xffffffffu) nb_arrive(NB_GATE, 256);
    mbar_spin(free_bar);
    WG_FENCE();
#pragma unroll
    for (int i = 0; i < 2 * NU; i++) wgmma_rs_n8(rs[i], make_uint4(ek[4 * i], ek[4 * i + 1], ek[4 * i + 2], ek[4 * i + 3]), qdesc(sb + OFF_ONE), 0);
    WG_COMMIT();
#pragma unroll
    for (int i = 0; i < NU; i++) stsm4(sl + (i >> 1) * 4 * SLAB + 2048 + (i & 1) * 512, vp[i].x, vp[i].y, vp[i].z, vp[i].w);
    if (NU == 4 || lane < 16) sts128(sl + (lane >> 4) * (4 * SLAB - 256) + 3072, 0x3F803F80u, 0x3F803F80u, 0x3F803F80u, 0x3F803F80u);
    WG_WAIT(0);
#pragma unroll
    for (int i = 0; i < 2 * NU; i++) {
      normalise(ek + 4 * i, rs[i]);
      stsm4(sl + (i >> 2) * 4 * SLAB + (i & 3) * 512, ek[4 * i], ek[4 * i + 1], ek[4 * i + 2], ek[4 * i + 3]);
    }
    asm volatile("fence.proxy.async.shared::cta;" ::: "memory");
  };
  auto contract = [&](float (&kc)[20], uint32_t stg, int acc_in) {
    WG_FENCE();
#pragma unroll
    for (int s = 0; s < 8; s++) wgmma_ss_n40(kc, qdesc(stg + s * SLAB), qdesc(stg + s * SLAB + 2048), s ? 1 : acc_in);
    WG_COMMIT();
    WG_WAIT(0);
  };
  uint32_t eq[32];
  {
    uint4 af[4], aq[4], vp[4];
    float kc[20];
#pragma unroll
    for (int u = 0; u < 4; u++) { af[u] = pack8(acc[u >> 1] + 16 + 8 * (u & 1)); vp[u] = pack8(acc[u >> 1] + 32 + 8 * (u & 1)); }
    const uint32_t hand = stg1 + 16384 + 8192 + w * 2048 + lane * 16;
    if (wg) {
      sts128(hand, af[2].x, af[2].y, af[2].z, af[2].w); sts128(hand + 512, af[3].x, af[3].y, af[3].z, af[3].w);
      sts128(hand + 1024, vp[2].x, vp[2].y, vp[2].z, vp[2].w); sts128(hand + 1536, vp[3].x, vp[3].y, vp[3].z, vp[3].w);
      nb_arrive(NB_HAND, 256);
    }
#pragma unroll
    for (int u = 0; u < 4; u++) aq[u] = pack8(acc[u >> 1] + 8 * (u & 1));
    if (wg == 0) {
      stage_k(std::integral_constant<int, 2>(), af, vp, stg0 + w * SLAB + lane * 16, BAR(MB_AUX));
      TS(13);
      nb_sync(NB_WG0, 128);
      contract(kc, stg0, 0);
      mbar_wait(BAR(MB_UFULL));
      TS(15);
      nb_sync(NB_HAND, 256);
      af[0] = lds128(hand); af[1] = lds128(hand + 512); vp[0] = lds128(hand + 1024); vp[1] = lds128(hand + 1536);
      nb_sync(NB_WG0, 128);
    }
    stage_k(std::integral_constant<int, 1>(), af, vp, stg1 + (wg ? w : 4 + w) * SLAB + lane * 16, BAR(MB_EMPTY + 15));
    TS(wg * 16 + 14);
    float p[4][8];
    if (wg) {
      nb_arrive(NB_ST0, 256);
    } else {
      uint4* pp = g_part + (size_t)(hp * 8 + rt) * 144 + t;
      uint32_t* pz = (uint32_t*)(pp - t + 128) + w * 16 + c * 8 + g;
      asm volatile("" : "+l"(pp), "+l"(pz));
      nb_sync(NB_ST0, 256);
      contract(kc, stg1, 1);
      TS(6);
      float kv[8];
#pragma unroll
      for (int i = 0; i < 8; i++) kv[i] = w & 2 ? kc[8 + i] : kc[i];
      st_x(pp, nz(pack_bf(kv[0], kv[1])), pack_bf(kv[2], kv[3]), pack_bf(kv[4], kv[5]), pack_bf(kv[6], kv[7]));
      if (c < 2) st_x32(pz, nz(fu(c ? kc[18] : kc[16])));
      TS(5);
    }
    SPLIT();
    WG_FENCE();
#pragma unroll
    for (int u = 0; u < 4; u++) wgmma_rs_n16(p[u], aq[u], qdesc(sb + OFF_PHI + (u & 1) * 512), 0);
    WG_COMMIT();
    WG_WAIT(0);
#pragma unroll
    for (int u = 0; u < 4; u++) {
      const uint32_t pw[4] = {pack_bf(p[u][0], p[u][2]), pack_bf(p[u][1], p[u][3]), pack_bf(p[u][4], p[u][6]), pack_bf(p[u][5], p[u][7])};
      dual_exp(pw, eq + 8 * u);
    }
    SPLIT();
  }
  TS(wg * 16 + 4);
  if (wg == 1) {
    mbar_wait(BAR(MB_UFULL));
    const uint4* ps = g_part + (size_t)hp * 8 * 144 + t;
    const uint32_t* zs = (const uint32_t*)(g_part + (size_t)(hp * 8 + (lane >> 4) * 4) * 144 + 128) + w * 16 + (lane & 15);
    uint4 v[8];
    uint32_t zv[4];
#pragma unroll 1
    for (int it = 0; it < SPIN_MAX; it++) {
#pragma unroll
      for (int i = 0; i < 8; i++) v[i] = ld_x(ps + i * 144);
#pragma unroll
      for (int i = 0; i < 4; i++) zv[i] = ld_x32(zs + i * 576);
      uint32_t m = min(min(zv[0], zv[1]), min(zv[2], zv[3]));
#pragma unroll
      for (int i = 0; i < 8; i++) m = min(m, v[i].x);
      if (__all_sync(0xffffffffu, m != 0)) break;
    }
    float s[8];
    WG_FENCE();
#pragma unroll
    for (int r = 0; r < 8; r++) wgmma_rs_n16(s, v[r], qdesc(sb + OFF_EYE), r);
    WG_COMMIT();
    float zsum = (uf(zv[0]) + uf(zv[1])) + (uf(zv[2]) + uf(zv[3]));
    zsum += __shfl_xor_sync(0xffffffffu, zsum, 16);
    const uint32_t z1 = pack_bf(zsum, 1.f);
    if (lane < 16) sts128(kvs + w * 768 + 512 + lane * 16, z1, z1, z1, z1);
    WG_WAIT(0);
    stsm4(kvs + w * 768 + lane * 16, pack_bf(s[0], s[1]), pack_bf(s[2], s[3]), pack_bf(s[4], s[5]), pack_bf(s[6], s[7]));
    asm volatile("fence.proxy.async.shared::cta;" ::: "memory");
    TS(22);
  }
  nb_sync(NB_KV, 256);
  {
    float n[8][12];
    WG_FENCE();
#pragma unroll
    for (int i = 0; i < 8; i++) wgmma_rs_n24(n[i], make_uint4(eq[4 * i], eq[4 * i + 1], eq[4 * i + 2], eq[4 * i + 3]), qdesc(kvs + (i & 3) * 768), 0);
    WG_COMMIT();
    uint32_t* od = (uint32_t*)(g_o + (size_t)((rt * 4 + wg * 2) * 32 + hp * 2) * 128) + w * 64 + lane;
    WG_WAIT(0);
#pragma unroll
    for (int u = 0; u < 4; u++) {
      float(&np)[12] = n[2 * u];
      const float(&nm)[12] = n[2 * u + 1];
      const float q0 = np[9] * rcp(nm[9]), q1 = np[11] * rcp(nm[11]);
      const float r0 = rcp(fmaf(nm[8], q0, fmaf(np[9], 1e-6f, np[8]))), r1 = rcp(fmaf(nm[10], q1, fmaf(np[11], 1e-6f, np[10])));
#pragma unroll
      for (int i = 0; i < 8; i++) np[i] = fmaf(nm[i], (i & 2) ? q1 : q0, np[i]);
      uint32_t* o = od + (u >> 1) * 16384 + (u & 1) * 512;
      o[0] = pack_bf(np[0] * r0, np[1] * r0);
      o[32] = pack_bf(np[2] * r1, np[3] * r1);
      o[256] = pack_bf(np[4] * r0, np[5] * r0);
      o[288] = pack_bf(np[6] * r1, np[7] * r1);
      if (u == 1) SPLIT();
    }
  }
  TS(wg * 16 + 7);
  nb_arrive(NB_ODONE, 288);
  if (wg) {
    const uint4* src = P.xs + X_Y + (oct * 32 + c * 8) * 256 + (2 * w + (g >> 2)) * 32 + i8 * 4 + (g & 3);
    __nv_bfloat16* dst = P.out + (size_t)((2 * w + (g >> 2)) * 256 + i8 * 16 + (g & 3) * 2) * 1024 + 512 + oct * 32 + c * 8;
    nb_sync(NB_GATE + 1, 160);
    nb_sync(NB_Y + w, 160);
    uint4 v[8];
#pragma unroll 1
    for (int it = 0; it < SPIN_MAX; it++) {
      uint32_t m = 0xffffffffu;
#pragma unroll
      for (int i = 0; i < 8; i++) v[i] = ld_x(src + i * 256);
#pragma unroll
      for (int i = 0; i < 8; i++) m = min(m, v[i].x);
      if (__all_sync(0xffffffffu, m != 0)) break;
    }
#pragma unroll
    for (int i = 0; i < 8; i++) *(uint4*)(dst + (size_t)((i >> 2) * 128 + ((i >> 1) & 1) * 8 + (i & 1)) * 1024) = tr_row(v, i);
    TS(31);
    GT(63);
    if (w == 0) TSDUMP(16);
    return;
  }
  mbar_wait(BAR(MB_WO));
  nb_sync(NB_BDONE, 288);
  TS(8);
  mbar_spin(BAR(MB_O));
  TS(9);
  constexpr uint64_t ha = mkdesc(0, 0, 128, 0), hb = mkdesc(0, 0, 1024, 1);
  constexpr uint32_t da0 = (uint32_t)mkdesc(stg1, 1024, 0, 0), db0 = (uint32_t)mkdesc(sb + OFF_W, 8192, 0, 0);
  const uint32_t ot = ((sb + OFF_T + 1023) & ~1023u) + w * 4096;
  auto store_half = [&](const float* oc, int hf) {
#pragma unroll
    for (int i = 0; i < 8; i += 2)
      stsm4(ot + hf * 2048 + (lane & 15) * 128 + (((i + (lane >> 4)) ^ lane) & 7) * 16, pack_bf(oc[4 * i], oc[4 * i + 1]),
            pack_bf(oc[4 * i + 2], oc[4 * i + 3]), pack_bf(oc[4 * i + 4], oc[4 * i + 5]), pack_bf(oc[4 * i + 6], oc[4 * i + 7]));
    asm volatile("fence.proxy.async.shared::cta;" ::: "memory");
    __syncwarp();
    e_store2d(&mout, ot + hf * 2048, (hp & 3) * 128 + hf * 64, (rt * 4 + (hp >> 2)) * 64 + w * 16);
  };
  float oc[64];
#pragma unroll 1
  for (int j = 0; j < 8; j++) {
    const int kb = (j + 7) & 7;
    if ((j & 1) && j < 6) mbar_spin(BAR(MB_O + 1) + 4 * (j - 1));
    WG_FENCE();
#pragma unroll
    for (int k = 0; k < 4; k++) wgmma_ss_n128(oc, ha | (da0 + 512 * kb + 128 * k), hb | (db0 + 1024 * kb + 128 * k), k ? 1 : j);
    WG_COMMIT();
  }
  WG_WAIT(0);
  TS(10);
  store_half(oc, 0);
  store_half(oc + 32, 1);
  asm volatile(ELECT "cp.async.bulk.commit_group;\n@p cp.async.bulk.wait_group.read 0;\n}\n" ::: "memory");
  TS(wg * 16 + 11);
  GT(61 + wg);
  if (w == 0) TSDUMP(0);
  if (w == 1) TSDUMP(48);
}

typedef CUresult (*EncodeFn)(CUtensorMap*, CUtensorMapDataType, cuuint32_t, void*, const cuuint64_t*, const cuuint64_t*,
                             const cuuint32_t*, const cuuint32_t*, CUtensorMapInterleave, CUtensorMapSwizzle,
                             CUtensorMapL2promotion, CUtensorMapFloatOOBfill);

}

extern "C" void kernel_launch(void* const* d_in, const int* in_sizes, int n_in, void* d_out, int out_size) {
  (void)in_sizes; (void)n_in; (void)out_size;
  void* fn = nullptr;
  cudaDriverEntryPointQueryResult qr;
  cudaGetDriverEntryPoint("cuTensorMapEncodeTiled", &fn, cudaEnableDefault, &qr);
  EncodeFn enc = (EncodeFn)fn;
  CUtensorMap mx, mw, mo, mu, mout;
  const cuuint32_t es[5] = {1, 1, 1, 1, 1};
  {
    cuuint64_t dims[2] = {512, 2048}, st[1] = {1024};
    cuuint32_t box[2] = {64, 128};
    enc(&mx, CU_TENSOR_MAP_DATA_TYPE_BFLOAT16, 2, d_in[0], dims, st, box, es, CU_TENSOR_MAP_INTERLEAVE_NONE,
        CU_TENSOR_MAP_SWIZZLE_128B, CU_TENSOR_MAP_L2_PROMOTION_L2_128B, CU_TENSOR_MAP_FLOAT_OOB_FILL_NONE);
  }
  {
    cuuint64_t dims[3] = {512, 512, 3}, st[2] = {3072, 1024};
    cuuint32_t box[3] = {32, 64, 3};
    enc(&mw, CU_TENSOR_MAP_DATA_TYPE_BFLOAT16, 3, d_in[1], dims, st, box, es, CU_TENSOR_MAP_INTERLEAVE_NONE,
        CU_TENSOR_MAP_SWIZZLE_64B, CU_TENSOR_MAP_L2_PROMOTION_L2_128B, CU_TENSOR_MAP_FLOAT_OOB_FILL_NONE);
  }
  {
    cuuint64_t dims[3] = {64, 512, 8}, st[2] = {1024, 128};
    cuuint32_t box[3] = {64, 64, 2};
    enc(&mo, CU_TENSOR_MAP_DATA_TYPE_BFLOAT16, 3, d_in[3], dims, st, box, es, CU_TENSOR_MAP_INTERLEAVE_NONE,
        CU_TENSOR_MAP_SWIZZLE_128B, CU_TENSOR_MAP_L2_PROMOTION_L2_128B, CU_TENSOR_MAP_FLOAT_OOB_FILL_NONE);
  }
  {
    cuuint64_t dims[4] = {512, 4, 16, 32}, st[3] = {16384, 1024, 65536};
    cuuint32_t box[4] = {64, 4, 16, 2};
    enc(&mu, CU_TENSOR_MAP_DATA_TYPE_BFLOAT16, 4, d_in[4], dims, st, box, es, CU_TENSOR_MAP_INTERLEAVE_NONE,
        CU_TENSOR_MAP_SWIZZLE_128B, CU_TENSOR_MAP_L2_PROMOTION_L2_128B, CU_TENSOR_MAP_FLOAT_OOB_FILL_NONE);
  }
  {
    cuuint64_t dims[2] = {1024, 2048}, st[1] = {2048};
    cuuint32_t box[2] = {64, 16};
    enc(&mout, CU_TENSOR_MAP_DATA_TYPE_BFLOAT16, 2, d_out, dims, st, box, es, CU_TENSOR_MAP_INTERLEAVE_NONE,
        CU_TENSOR_MAP_SWIZZLE_128B, CU_TENSOR_MAP_L2_PROMOTION_NONE, CU_TENSOR_MAP_FLOAT_OOB_FILL_NONE);
  }
  Params P;
  P.x = (const __nv_bfloat16*)d_in[0];
  P.wphi = (const __nv_bfloat16*)d_in[2];
  P.wo = (const __nv_bfloat16*)d_in[3];
  P.logA = (const __nv_bfloat16*)d_in[5];
  P.Aim = (const __nv_bfloat16*)d_in[6];
  P.Cre = (const __nv_bfloat16*)d_in[7];
  P.Cim = (const __nv_bfloat16*)d_in[8];
  P.logdt = (const __nv_bfloat16*)d_in[9];
  P.Dskip = (const __nv_bfloat16*)d_in[10];
  P.out = (__nv_bfloat16*)d_out;
  cudaGetSymbolAddress((void**)&P.xs, g_x);
  P.ts = nullptr;
  cudaFuncSetAttribute(fused_kernel, cudaFuncAttributeMaxDynamicSharedMemorySize, SMEM_BYTES);
  fused_kernel<<<NCTA, NTHREADS, SMEM_BYTES>>>(P, mx, mw, mo, mu, mout);
}
```

```cpp
#include <cuda_runtime.h>
#include <cuda_bf16.h>
#include <cuda_fp16.h>
#include <cuda.h>
#include <stdint.h>
#include <type_traits>

#define DBG_TS 0

namespace {

constexpr int NTHREADS = 512;
constexpr int NCTA = 128;
constexpr int OFF_W = 0;
constexpr int OFF_X = 98304;
constexpr int OFF_U = OFF_X + 65536;
constexpr int U_CH = 4416, U_ODD = 2240, U_PAD = 128;
constexpr int OFF_STG0 = OFF_U + 18432;
constexpr int SLAB = 3328;
constexpr int OFF_T = OFF_STG0 + 8 * SLAB;
constexpr int T_CH = 5216;
constexpr int T_D = 0;
constexpr int T_5 = 2144;
constexpr int T_3 = T_5 + 384;
constexpr int T_7 = T_5 + 1024;
constexpr int T_9 = T_7 + 320;
constexpr int T_KC = T_9 + 320;
constexpr int T_ST = T_5 - 1024;
constexpr int OFF_PHI = OFF_T + 4 * T_CH;
constexpr int OFF_EYE = OFF_PHI + 1024, OFF_ONE = OFF_EYE + 512;
constexpr int OFF_BAR = OFF_ONE + 256;
constexpr int SMEM_BYTES = OFF_BAR + 512 + 256 * DBG_TS;
constexpr uint32_t SB = 1024;
static_assert(T_KC + 2 * 656 <= T_CH, "table size");
static_assert(SMEM_BYTES <= 232448, "smem");
constexpr int MB_URAW = 0, MB_FULL = 1  , MB_WO = 17, MB_UFULL = 18, MB_O = 19  ,
              MB_EMPTY = 23  , MB_AUX = 39;
__host__ __device__ constexpr uint32_t BAR(int i) { return SB + OFF_BAR + 8 * i; }
constexpr int NB_WG0 = 1, NB_ODONE = 2, NB_ST0 = 3, NB_HAND = 4, NB_KV = 5, NB_YZ = 6, NB_INIT = 7, NB_PREP = 8, NB_PROD = 9, NB_KREAD = 10,
              NB_BDONE = 11, NB_GATE = 12  , NB_HELP = 14, NB_YZ0 = 15, NB_Y = 7  ;
#define GATEV 2
constexpr int U_AT = 2;
constexpr int ZERO_STEP = 12;
constexpr int SPIN_MAX = 1 << 16;

constexpr int X_CNT = 0;
constexpr int X_PART = 256;
constexpr int X_O = X_PART + 16 * 8 * 144;
constexpr int X_Y = X_O + 32 * 32 * 128;
constexpr int X_UT = X_Y + 512 * 8 * 32;
constexpr int X_SIZE = X_UT + 512 * (U_CH / 16);
__device__ __align__(128) uint4 g_x[X_SIZE];
extern __shared__ uint8_t smem_raw[];
#define TS(i) do {} while (0)
#define TS1(i) do {} while (0)
#define GT(i) do {} while (0)
#define TSDUMP(base) do {} while (0)

__device__ __forceinline__ uint32_t smem_u32(const void* p) { return (uint32_t)__cvta_generic_to_shared(p); }
__device__ __forceinline__ void mbar_arrive(uint32_t b) {
  asm volatile("mbarrier.arrive.shared::cta.b64 _, [%0];" ::"r"(b) : "memory");
}
__device__ __forceinline__ void mbar_wait(uint32_t b) {
  uint32_t done = 0;
#pragma unroll 1
  for (int i = 0; i < SPIN_MAX && !done; i++) {
    asm volatile("{\n.reg .pred p;\nmbarrier.try_wait.parity.shared::cta.b64 p, [%1], 0, 4000;\nselp.u32 %0, 1, 0, p;\n}\n"
                 : "=r"(done) : "r"(b) : "memory");
  }
}
__device__ __forceinline__ void mbar_spin(uint32_t b) {
  uint32_t done = 0;
#pragma unroll 1
  for (int i = 0; i < (SPIN_MAX << 4) && !done; i++) {
    asm volatile("{\n.reg .pred p;\nmbarrier.try_wait.parity.shared::cta.b64 p, [%1], 0;\nselp.u32 %0, 1, 0, p;\n}\n"
                 : "=r"(done) : "r"(b) : "memory");
  }
}
__device__ __forceinline__ void mbar_init(uint32_t b, int n) {
  asm volatile("mbarrier.init.shared::cta.b64 [%0], %1;" ::"r"(b), "r"(n) : "memory");
}
__device__ __forceinline__ void mbar_expect(uint32_t b, int bytes) {
  asm volatile("mbarrier.arrive.expect_tx.shared::cta.b64 _, [%0], %1;" ::"r"(b), "r"(bytes) : "memory");
}
__device__ __forceinline__ void nb_sync(int id, int n) { asm volatile("bar.sync %0, %1;" ::"r"(id), "r"(n) : "memory"); }
__device__ __forceinline__ void nb_arrive(int id, int n) { asm volatile("bar.arrive %0, %1;" ::"r"(id), "r"(n) : "memory"); }
#define ELECT "{\n.reg .pred p;\nelect.sync _|p, 0xffffffff;\n@p "
__device__ __forceinline__ void e_arrive(uint32_t b) {
  asm volatile(ELECT "mbarrier.arrive.shared::cta.b64 _, [%0];\n}\n" ::"r"(b) : "memory");
}
__device__ __forceinline__ void e_expect(uint32_t b, int bytes) {
  asm volatile(ELECT "mbarrier.arrive.expect_tx.shared::cta.b64 _, [%0], %1;\n}\n" ::"r"(b), "r"(bytes) : "memory");
}
__device__ __forceinline__ void e_tma2d(uint32_t dst, const CUtensorMap* m, uint32_t bar, int c0, int c1) {
  asm volatile(ELECT "cp.async.bulk.tensor.2d.shared::cluster.global.mbarrier::complete_tx::bytes [%0], [%1, {%3,%4}], [%2];\n}\n"
               ::"r"(dst), "l"(m), "r"(bar), "r"(c0), "r"(c1) : "memory");
}
__device__ __forceinline__ void e_tma3d(uint32_t dst, const CUtensorMap* m, uint32_t bar, int c0, int c1, int c2) {
  asm volatile(ELECT "cp.async.bulk.tensor.3d.shared::cluster.global.mbarrier::complete_tx::bytes [%0], [%1, {%3,%4,%5}], [%2];\n}\n"
               ::"r"(dst), "l"(m), "r"(bar), "r"(c0), "r"(c1), "r"(c2) : "memory");
}
__device__ __forceinline__ void e_tma4d(uint32_t dst, const CUtensorMap* m, uint32_t bar, int c0, int c3) {
  asm volatile(ELECT "cp.async.bulk.tensor.4d.shared::cluster.global.mbarrier::complete_tx::bytes [%0], [%1, {%3,%5,%5,%4}], [%2];\n}\n"
               ::"r"(dst), "l"(m), "r"(bar), "r"(c0), "r"(c3), "r"(0) : "memory");
}
__device__ __forceinline__ void e_bulk(uint32_t dst, const void* src, int bytes, uint32_t bar) {
  asm volatile(ELECT "cp.async.bulk.shared::cluster.global.mbarrier::complete_tx::bytes [%0], [%1], %2, [%3];\n}\n"
               ::"r"(dst), "l"(src), "r"(bytes), "r"(bar) : "memory");
}
__device__ __forceinline__ void e_prefetch(const void* p, int bytes) {
  asm volatile(ELECT "cp.async.bulk.prefetch.L2.global [%0], %1;\n}\n" ::"l"(p), "r"(bytes) : "memory");
}
__device__ __forceinline__ void e_store2d(const CUtensorMap* m, uint32_t src, int c0, int c1) {
  asm volatile(ELECT "cp.async.bulk.tensor.2d.global.shared::cta.bulk_group [%0, {%2,%3}], [%1];\n}\n"
               ::"l"(m), "r"(src), "r"(c0), "r"(c1) : "memory");
}
__host__ __device__ constexpr uint64_t mkdesc(uint32_t addr, uint32_t lbo, uint32_t sbo, int swz) {
  return (uint64_t)((addr & 0x3FFFF) >> 4) | ((uint64_t)(lbo >> 4) << 16) | ((uint64_t)(sbo >> 4) << 32) |
         ((uint64_t)swz << 62);
}
#define SPLIT() asm volatile("{\n.reg .pred p;\nsetp.eq.u32 p, %0, %1;\n@p exit;\n}\n" ::"r"(blockIdx.y), "n"(__LINE__) : "memory")
#define SPLITN(n) asm volatile("{\n.reg .pred p;\nsetp.eq.u32 p, %0, %1;\n@p exit;\n}\n" ::"r"(blockIdx.y), "r"(4096 + (n)) : "memory")
#define WG_FENCE() asm volatile("wgmma.fence.sync.aligned;" ::: "memory")
#define WG_COMMIT() asm volatile("wgmma.commit_group.sync.aligned;" ::: "memory")
#define WG_WAIT(n) asm volatile("wgmma.wait_group.sync.aligned " #n ";" ::: "memory")

__device__ __forceinline__ void mma(float& d0, float& d1, float& d2, float& d3, uint32_t a0, uint32_t a1, uint32_t a2,
                                    uint32_t a3, uint32_t b0, uint32_t b1) {
  asm volatile("mma.sync.aligned.m16n8k16.row.col.f32.bf16.bf16.f32 {%0,%1,%2,%3},{%4,%5,%6,%7},{%8,%9},{%0,%1,%2,%3};"
               : "+f"(d0), "+f"(d1), "+f"(d2), "+f"(d3)
               : "r"(a0), "r"(a1), "r"(a2), "r"(a3), "r"(b0), "r"(b1));
}
__device__ __forceinline__ void mmac(float (&d)[4], uint32_t a0, uint32_t a1, uint32_t a2, uint32_t a3, uint32_t b0,
                                     uint32_t b1, const float (&c)[4]) {
  asm volatile("mma.sync.aligned.m16n8k16.row.col.f32.bf16.bf16.f32 {%0,%1,%2,%3},{%4,%5,%6,%7},{%8,%9},{%10,%11,%12,%13};"
               : "=f"(d[0]), "=f"(d[1]), "=f"(d[2]), "=f"(d[3])
               : "r"(a0), "r"(a1), "r"(a2), "r"(a3), "r"(b0), "r"(b1), "f"(c[0]), "f"(c[1]), "f"(c[2]), "f"(c[3]));
}
__device__ __forceinline__ void mma_h(float (&d)[4], const uint32_t (&a)[4], uint32_t b0, uint32_t b1) {
  asm volatile("mma.sync.aligned.m16n8k16.row.col.f32.f16.f16.f32 {%0,%1,%2,%3},{%4,%5,%6,%7},{%8,%9},{%0,%1,%2,%3};"
               : "+f"(d[0]), "+f"(d[1]), "+f"(d[2]), "+f"(d[3]) : "r"(a[0]), "r"(a[1]), "r"(a[2]), "r"(a[3]), "r"(b0), "r"(b1));
}
__device__ __forceinline__ void mma0(float& d0, float& d1, float& d2, float& d3, uint32_t a0, uint32_t a1, uint32_t a2,
                                     uint32_t a3, uint32_t b0, uint32_t b1) {
  asm volatile("mma.sync.aligned.m16n8k16.row.col.f32.bf16.bf16.f32 {%0,%1,%2,%3},{%4,%5,%6,%7},{%8,%9},{%10,%10,%10,%10};"
               : "=f"(d0), "=f"(d1), "=f"(d2), "=f"(d3)
               : "r"(a0), "r"(a1), "r"(a2), "r"(a3), "r"(b0), "r"(b1), "f"(0.f));
}
__device__ __forceinline__ uint32_t pack_bf(float lo, float hi) {
  uint32_t r;
  asm("cvt.rn.bf16x2.f32 %0, %1, %2;" : "=r"(r) : "f"(hi), "f"(lo));
  return r;
}
__device__ __forceinline__ float bf_lo(uint32_t w) { return __uint_as_float(w << 16); }
__device__ __forceinline__ float bf_hi(uint32_t w) { return __uint_as_float(w & 0xffff0000u); }
__device__ __forceinline__ float bf_round(float x) { return __bfloat162float(__float2bfloat16_rn(x)); }
__device__ __forceinline__ uint32_t bmax2(uint32_t a, uint32_t b) {
  uint32_t r; asm("max.bf16x2 %0, %1, %2;" : "=r"(r) : "r"(a), "r"(b)); return r;
}
__device__ __forceinline__ uint32_t bmin2(uint32_t a, uint32_t b) {
  uint32_t r; asm("min.bf16x2 %0, %1, %2;" : "=r"(r) : "r"(a), "r"(b)); return r;
}
__device__ __forceinline__ float ex2(float x) { float r; asm("ex2.approx.ftz.f32 %0, %1;" : "=f"(r) : "f"(x)); return r; }
__device__ __forceinline__ float rcp(float x) { float r; asm("rcp.approx.ftz.f32 %0, %1;" : "=f"(r) : "f"(x)); return r; }
__device__ __forceinline__ void ldsm4(uint32_t (&r)[4], uint32_t a) {
  asm volatile("ldmatrix.sync.aligned.m8n8.x4.shared.b16 {%0,%1,%2,%3}, [%4];"
               : "=r"(r[0]), "=r"(r[1]), "=r"(r[2]), "=r"(r[3]) : "r"(a) : "memory");
}
__device__ __forceinline__ void ldsm4t(uint32_t (&r)[4], uint32_t a) {
  asm volatile("ldmatrix.sync.aligned.m8n8.x4.trans.shared.b16 {%0,%1,%2,%3}, [%4];"
               : "=r"(r[0]), "=r"(r[1]), "=r"(r[2]), "=r"(r[3]) : "r"(a) : "memory");
}
__device__ __forceinline__ void stsm4(uint32_t a, uint32_t r0, uint32_t r1, uint32_t r2, uint32_t r3) {
  asm volatile("stmatrix.sync.aligned.m8n8.x4.shared.b16 [%0], {%1,%2,%3,%4};"
               ::"r"(a), "r"(r0), "r"(r1), "r"(r2), "r"(r3) : "memory");
}
__device__ __forceinline__ uint32_t lds32(uint32_t a) {
  uint32_t r; asm volatile("ld.shared.u32 %0, [%1];" : "=r"(r) : "r"(a) : "memory"); return r;
}
__device__ __forceinline__ uint32_t lds16(uint32_t a) {
  uint32_t r; asm volatile("{\n.reg .u16 h;\nld.shared.u16 h, [%1];\ncvt.u32.u16 %0, h;\n}\n" : "=r"(r) : "r"(a) : "memory"); return r;
}
__device__ __forceinline__ uint2 lds64(uint32_t a) {
  uint2 r; asm volatile("ld.shared.v2.u32 {%0,%1}, [%2];" : "=r"(r.x), "=r"(r.y) : "r"(a) : "memory"); return r;
}
__device__ __forceinline__ uint4 lds128(uint32_t a) {
  uint4 r;
  asm volatile("ld.shared.v4.u32 {%0,%1,%2,%3}, [%4];" : "=r"(r.x), "=r"(r.y), "=r"(r.z), "=r"(r.w) : "r"(a) : "memory");
  return r;
}
__device__ __forceinline__ void sts32(uint32_t a, uint32_t v) { asm volatile("st.shared.u32 [%0], %1;" ::"r"(a), "r"(v) : "memory"); }
__device__ __forceinline__ void sts16(uint32_t a, uint32_t v) {
  asm volatile("{\n.reg .u16 h;\ncvt.u16.u32 h, %1;\nst.shared.u16 [%0], h;\n}\n" ::"r"(a), "r"(v) : "memory");
}
__device__ __forceinline__ void sts64(uint32_t a, uint32_t x, uint32_t y) {
  asm volatile("st.shared.v2.u32 [%0], {%1,%2};" ::"r"(a), "r"(x), "r"(y) : "memory");
}
__device__ __forceinline__ void sts128(uint32_t a, uint32_t x, uint32_t y, uint32_t z, uint32_t w) {
  asm volatile("st.shared.v4.u32 [%0], {%1,%2,%3,%4};" ::"r"(a), "r"(x), "r"(y), "r"(z), "r"(w) : "memory");
}
__device__ __forceinline__ uint4 ld_x(const uint4* p) {
  uint4 r;
  asm volatile("{\n.reg .b128 t;\nld.relaxed.gpu.global.b128 t, [%4];\nmov.b128 {%0,%1,%2,%3}, t;\n}\n"
               : "=r"(r.x), "=r"(r.y), "=r"(r.z), "=r"(r.w) : "l"(p) : "memory");
  return r;
}
__device__ __forceinline__ uint32_t ld_x32(const uint32_t* p) {
  uint32_t r; asm volatile("ld.relaxed.gpu.global.u32 %0, [%1];" : "=r"(r) : "l"(p) : "memory"); return r;
}
__device__ __forceinline__ void st_x(uint4* p, uint32_t x, uint32_t y, uint32_t z, uint32_t w) {
  asm volatile("{\n.reg .b128 t;\nmov.b128 t, {%1,%2,%3,%4};\nst.relaxed.gpu.global.b128 [%0], t;\n}\n"
               ::"l"(p), "r"(x), "r"(y), "r"(z), "r"(w) : "memory");
}
__device__ __forceinline__ void st_x32(uint32_t* p, uint32_t x) {
  asm volatile("st.relaxed.gpu.global.u32 [%0], %1;" ::"l"(p), "r"(x) : "memory");
}
__device__ __forceinline__ uint32_t nz(uint32_t w) { return max(w, 1u); }
__device__ __forceinline__ uint32_t fu(float x) { return __float_as_uint(x); }
__device__ __forceinline__ float uf(uint32_t x) { return __uint_as_float(x); }

__device__ __forceinline__ void wgmma_ss_n96(float (&d)[48], uint64_t da, uint64_t db, int sc) {
  asm volatile("{\n.reg .pred p;\nsetp.ne.b32 p, %50, 0;\n"
      "wgmma.mma_async.sync.aligned.m64n96k16.f32.bf16.bf16 "
      "{%0,%1,%2,%3,%4,%5,%6,%7,%8,%9,%10,%11,%12,%13,%14,%15,%16,%17,%18,%19,%20,%21,%22,%23,%24,%25,%26,%27,%28,%29,%30,%31,%32,%33,%34,%35,%36,%37,%38,%39,%40,%41,%42,%43,%44,%45,%46,%47}, "
      "%48, %49, p, 1, 1, 0, 1;\n}\n"
      : "+f"(d[0]), "+f"(d[1]), "+f"(d[2]), "+f"(d[3]), "+f"(d[4]), "+f"(d[5]), "+f"(d[6]), "+f"(d[7]),
        "+f"(d[8]), "+f"(d[9]), "+f"(d[10]), "+f"(d[11]), "+f"(d[12]), "+f"(d[13]), "+f"(d[14]), "+f"(d[15]),
        "+f"(d[16]), "+f"(d[17]), "+f"(d[18]), "+f"(d[19]), "+f"(d[20]), "+f"(d[21]), "+f"(d[22]), "+f"(d[23]),
        "+f"(d[24]), "+f"(d[25]), "+f"(d[26]), "+f"(d[27]), "+f"(d[28]), "+f"(d[29]), "+f"(d[30]), "+f"(d[31]),
        "+f"(d[32]), "+f"(d[33]), "+f"(d[34]), "+f"(d[35]), "+f"(d[36]), "+f"(d[37]), "+f"(d[38]), "+f"(d[39]),
        "+f"(d[40]), "+f"(d[41]), "+f"(d[42]), "+f"(d[43]), "+f"(d[44]), "+f"(d[45]), "+f"(d[46]), "+f"(d[47])
      : "l"(da), "l"(db), "r"(sc));
}

__device__ __forceinline__ void wgmma_ss_n128(float (&d)[64], uint64_t da, uint64_t db, int sc) {
  asm volatile("{\n.reg .pred p;\nsetp.ne.b32 p, %66, 0;\n"
      "wgmma.mma_async.sync.aligned.m64n128k16.f32.bf16.bf16 "
      "{%0,%1,%2,%3,%4,%5,%6,%7,%8,%9,%10,%11,%12,%13,%14,%15,%16,%17,%18,%19,%20,%21,%22,%23,%24,%25,%26,%27,%28,%29,%30,%31,%32,%33,%34,%35,%36,%37,%38,%39,%40,%41,%42,%43,%44,%45,%46,%47,%48,%49,%50,%51,%52,%53,%54,%55,%56,%57,%58,%59,%60,%61,%62,%63}, "
      "%64, %65, p, 1, 1, 0, 1;\n}\n"
      : "+f"(d[0]), "+f"(d[1]), "+f"(d[2]), "+f"(d[3]), "+f"(d[4]), "+f"(d[5]), "+f"(d[6]), "+f"(d[7]),
        "+f"(d[8]), "+f"(d[9]), "+f"(d[10]), "+f"(d[11]), "+f"(d[12]), "+f"(d[13]), "+f"(d[14]), "+f"(d[15]),
        "+f"(d[16]), "+f"(d[17]), "+f"(d[18]), "+f"(d[19]), "+f"(d[20]), "+f"(d[21]), "+f"(d[22]), "+f"(d[23]),
        "+f"(d[24]), "+f"(d[25]), "+f"(d[26]), "+f"(d[27]), "+f"(d[28]), "+f"(d[29]), "+f"(d[30]), "+f"(d[31]),
        "+f"(d[32]), "+f"(d[33]), "+f"(d[34]), "+f"(d[35]), "+f"(d[36]), "+f"(d[37]), "+f"(d[38]), "+f"(d[39]),
        "+f"(d[40]), "+f"(d[41]), "+f"(d[42]), "+f"(d[43]), "+f"(d[44]), "+f"(d[45]), "+f"(d[46]), "+f"(d[47]),
        "+f"(d[48]), "+f"(d[49]), "+f"(d[50]), "+f"(d[51]), "+f"(d[52]), "+f"(d[53]), "+f"(d[54]), "+f"(d[55]),
        "+f"(d[56]), "+f"(d[57]), "+f"(d[58]), "+f"(d[59]), "+f"(d[60]), "+f"(d[61]), "+f"(d[62]), "+f"(d[63])
      : "l"(da), "l"(db), "r"(sc));
}

__device__ __forceinline__ void wgmma_ss_n40(float (&d)[20], uint64_t da, uint64_t db, int sc) {
  asm volatile("{\n.reg .pred p;\nsetp.ne.b32 p, %22, 0;\n"
      "wgmma.mma_async.sync.aligned.m64n40k16.f32.bf16.bf16 "
      "{%0,%1,%2,%3,%4,%5,%6,%7,%8,%9,%10,%11,%12,%13,%14,%15,%16,%17,%18,%19}, "
      "%20, %21, p, 1, 1, 1, 1;\n}\n"
      : "+f"(d[0]), "+f"(d[1]), "+f"(d[2]), "+f"(d[3]), "+f"(d[4]), "+f"(d[5]), "+f"(d[6]), "+f"(d[7]),
        "+f"(d[8]), "+f"(d[9]), "+f"(d[10]), "+f"(d[11]), "+f"(d[12]), "+f"(d[13]), "+f"(d[14]), "+f"(d[15]),
        "+f"(d[16]), "+f"(d[17]), "+f"(d[18]), "+f"(d[19])
      : "l"(da), "l"(db), "r"(sc));
}

__device__ __forceinline__ void wgmma_rs_n8(float (&d)[4], const uint4& a, uint64_t db, int sc) {
  asm volatile("{\n.reg .pred p;\nsetp.ne.b32 p, %9, 0;\n"
      "wgmma.mma_async.sync.aligned.m64n8k16.f32.bf16.bf16 "
      "{%0,%1,%2,%3}, "
      "{%4,%5,%6,%7}, %8, p, 1, 1, 1;\n}\n"
      : "+f"(d[0]), "+f"(d[1]), "+f"(d[2]), "+f"(d[3])
      : "r"(a.x), "r"(a.y), "r"(a.z), "r"(a.w), "l"(db), "r"(sc));
}

__device__ __forceinline__ void wgmma_rs_n16(float (&d)[8], const uint4& a, uint64_t db, int sc) {
  asm volatile("{\n.reg .pred p;\nsetp.ne.b32 p, %13, 0;\n"
      "wgmma.mma_async.sync.aligned.m64n16k16.f32.bf16.bf16 "
      "{%0,%1,%2,%3,%4,%5,%6,%7}, "
      "{%8,%9,%10,%11}, %12, p, 1, 1, 1;\n}\n"
      : "+f"(d[0]), "+f"(d[1]), "+f"(d[2]), "+f"(d[3]), "+f"(d[4]), "+f"(d[5]), "+f"(d[6]), "+f"(d[7])
      : "r"(a.x), "r"(a.y), "r"(a.z), "r"(a.w), "l"(db), "r"(sc));
}

__device__ __forceinline__ void wgmma_rs_n24(float (&d)[12], const uint4& a, uint64_t db, int sc) {
  asm volatile("{\n.reg .pred p;\nsetp.ne.b32 p, %17, 0;\n"
      "wgmma.mma_async.sync.aligned.m64n24k16.f32.bf16.bf16 "
      "{%0,%1,%2,%3,%4,%5,%6,%7,%8,%9,%10,%11}, "
      "{%12,%13,%14,%15}, %16, p, 1, 1, 1;\n}\n"
      : "+f"(d[0]), "+f"(d[1]), "+f"(d[2]), "+f"(d[3]), "+f"(d[4]), "+f"(d[5]), "+f"(d[6]), "+f"(d[7]),
        "+f"(d[8]), "+f"(d[9]), "+f"(d[10]), "+f"(d[11])
      : "r"(a.x), "r"(a.y), "r"(a.z), "r"(a.w), "l"(db), "r"(sc));
}

struct Params {
  const __nv_bfloat16 *logA, *Aim, *Cre, *Cim, *logdt, *Dskip, *x, *wphi, *wo;
  __nv_bfloat16* out;
  uint4* xs;
  long long* ts;
};

__device__ __forceinline__ uint4 tr_row(const uint4 (&v)[8], int i) {
  uint32_t o[4];
#pragma unroll
  for (int m = 0; m < 4; m++) {
    const uint4 &ra = v[2 * m], &rb = v[2 * m + 1];
    const int k = i >> 1;
    const uint32_t xa = k == 0 ? ra.x : k == 1 ? ra.y : k == 2 ? ra.z : ra.w;
    const uint32_t xb = k == 0 ? rb.x : k == 1 ? rb.y : k == 2 ? rb.z : rb.w;
    o[m] = __byte_perm(xa, xb, (i & 1) ? 0x7632 : 0x5410);
  }
  return make_uint4(o[0], o[1], o[2], o[3]);
}

struct cpx { float r, i; };
__device__ __forceinline__ cpx csq(cpx a) { return {a.r * a.r - a.i * a.i, 2.f * (a.r * a.i)}; }
__device__ __forceinline__ cpx polar(float e, float t) {
  const float m = ex2(e);
  return {m * __cosf(t), m * __sinf(t)};
}

struct KgenRaw { uint32_t la, ai, cr, ci, ldt; };
__device__ __forceinline__ KgenRaw kgen_load(const Params& P, int d, int unit, int lane, int on) {
  const int o = d * 64 + unit * 32 + lane;
  KgenRaw r = {0, 0, 0, 0, 0};
  asm volatile("{\n.reg .pred p;\nsetp.ne.b32 p, %10, 0;\n@p ld.global.nc.u32 %0, [%5];\n@p ld.global.nc.u32 %1, [%6];\n"
               "@p ld.global.nc.u32 %2, [%7];\n@p ld.global.nc.u32 %3, [%8];\n@p ld.global.nc.u16 %4, [%9];\n}\n"
               : "+r"(r.la), "+r"(r.ai), "+r"(r.cr), "+r"(r.ci), "+r"(r.ldt)
               : "l"((const uint32_t*)P.logA + o), "l"((const uint32_t*)P.Aim + o), "l"((const uint32_t*)P.Cre + o),
                 "l"((const uint32_t*)P.Cim + o), "l"(P.logdt + d), "r"(on));
  return r;
}
struct hc { __half2 r, i; };
struct cpx2 { cpx a, b; };
__device__ __forceinline__ cpx2 csq2(const cpx2& v) { return {csq(v.a), csq(v.b)}; }
__device__ __forceinline__ hc toh(const cpx2& v) { return {__floats2half2_rn(v.a.r, v.b.r), __floats2half2_rn(v.a.i, v.b.i)}; }
__device__ __forceinline__ hc hmul(const hc& z, const hc& w) {
  return {__hfma2(z.r, w.r, __hneg2(__hmul2(z.i, w.i))), __hfma2(z.r, w.i, __hmul2(z.i, w.r))};
}
__device__ __forceinline__ hc hmulc(const hc& z, const hc& w) {
  return {__hfma2(z.r, w.r, __hmul2(z.i, w.i)), __hfma2(z.i, w.r, __hneg2(__hmul2(z.r, w.i)))};
}
__device__ __forceinline__ uint32_t hu(__half2 v) { return *(const uint32_t*)&v; }
__device__ __forceinline__ __half2 uh(uint32_t v) { return *(const __half2*)&v; }

struct KgenAddr { uint32_t sa, lb, lm[4]; };
__device__ __forceinline__ KgenAddr kgen_addr(int lane, uint32_t buf) {
  KgenAddr a;
  a.sa = buf + (lane & 7) * 128 + ((((lane >> 3) ^ lane) & 7) << 4);
  const int q = lane >> 4;
  const uint32_t b = buf + ((lane >> 3) & 1) * 1024 + q * 128;
  a.lb = b + (((lane ^ q) & 7) << 4);
  a.lm[0] = b + (q << 4);
  a.lm[1] = b + ((1 ^ q) << 4);
  a.lm[2] = b + (((2 + (lane & 1)) ^ q) << 4);
  a.lm[3] = b + (((4 + (lane & 3)) ^ q) << 4);
  asm volatile("" : "+r"(a.sa), "+r"(a.lb), "+r"(a.lm[0]), "+r"(a.lm[1]), "+r"(a.lm[2]), "+r"(a.lm[3]));
  return a;
}
__device__ __forceinline__ void kgen_unit(const KgenRaw& r, const KgenAddr& ad, uint32_t zero, float (&k)[5][4], float& k2048, float& sc) {
  const float dt = bf_round(expf(bf_lo(r.ldt)));
  const uint32_t ar = pack_bf(ex2(bf_lo(r.la) * 1.4426950408889634f), ex2(bf_hi(r.la) * 1.4426950408889634f));
  const float ca = dt * -1.4426950408889634f, a0 = bf_lo(ar) * ca, a1 = bf_hi(ar) * ca;
  const float f0 = bf_lo(r.ai) * dt, f1 = bf_hi(r.ai) * dt;
  const float r0 = f0 * 20.21267777267071f, r1 = f1 * 20.21267777267071f;
  const uint32_t cm = __vmaxu2(r.cr & 0x7fff7fffu, r.ci & 0x7fff7fffu);
  const uint32_t ex = min(max(__reduce_max_sync(0xffffffffu, max(cm >> 16, cm & 0xffffu)) >> 7, 1u), 253u);
  const float cs = uf((254u - ex) << 23);
  sc = 2.f * dt * uf(ex << 23);
  const cpx2 C = {{bf_lo(r.cr) * cs, bf_lo(r.ci) * -cs}, {bf_hi(r.cr) * cs, bf_hi(r.ci) * -cs}};
  auto put = [&](const hc (&v)[8]) {
    stsm4(ad.sa, hu(v[0].r), hu(v[1].r), hu(v[2].r), hu(v[3].r));
    stsm4(ad.sa + 1024, hu(v[0].i), hu(v[1].i), hu(v[2].i), hu(v[3].i));
    stsm4(ad.sa ^ 64, hu(v[4].r), hu(v[5].r), hu(v[6].r), hu(v[7].r));
    stsm4((ad.sa ^ 64) + 1024, hu(v[4].i), hu(v[5].i), hu(v[6].i), hu(v[7].i));
    __syncwarp();
  };
  auto get = [&](uint32_t (&o)[4][4], uint32_t a) {
#pragma unroll
    for (int i = 0; i < 4; i++) ldsm4(o[i], (a ^ (i << 5)) + i * 256);
  };
  auto at = [](const uint32_t (&o)[4][4], int s) { return hc{uh(o[s >> 1][2 * (s & 1)]), uh(o[s >> 1][2 * (s & 1) + 1])}; };
  uint32_t A[8][4];
  auto tile = [&](int j, const uint32_t (&B)[4][4]) {
    k[j][0] = k[j][1] = k[j][2] = k[j][3] = 0.f;
#pragma unroll
    for (int s = 0; s < 8; s++) mma_h(k[j], A[s], B[s >> 1][2 * (s & 1)], B[s >> 1][2 * (s & 1) + 1]);
  };
  const cpx2 w1 = {polar(a0, f0), polar(a1, f1)};
  const cpx2 w127 = {polar(a0 * 127.f, (r0 - rintf(r0)) * 6.283185307179586f), polar(a1 * 127.f, (r1 - rintf(r1)) * 6.283185307179586f)};
  const cpx2 w2 = csq2(w1), w4 = csq2(w2);
  uint32_t T0[4][4], X[4][4], M[3][4][4];
  {
    hc t[8];
    t[0] = {uh(0x3C003C00u), uh(0u)}; t[1] = toh(w1); t[2] = toh(w2); t[4] = toh(w4);
    t[3] = hmul(t[1], t[2]); t[5] = hmul(t[1], t[4]); t[6] = hmul(t[2], t[4]); t[7] = hmul(t[3], t[4]);
    put(t); get(T0, ad.lb);
  }
  const cpx2 w8 = csq2(w4), w16 = csq2(w8), w32 = csq2(w16), w64 = csq2(w32);
  {
    const hc m8 = toh(w8), m16 = toh(w16), m32 = toh(w32);
    hc a[8];
    a[0] = toh(C); a[1] = hmulc(a[0], m8);
    a[2] = hmulc(a[0], m16); a[3] = hmulc(a[1], m16);
#pragma unroll
    for (int i = 0; i < 4; i++) a[4 + i] = hmulc(a[i], m32);
    put(a); get(X, ad.lb);
  }
    const cpx2 w128 = {{w127.a.r * w1.a.r - w127.a.i * w1.a.i, w127.a.r * w1.a.i + w127.a.i * w1.a.r},
                     {w127.b.r * w1.b.r - w127.b.i * w1.b.i, w127.b.r * w1.b.i + w127.b.i * w1.b.r}};
  const cpx2 w256 = csq2(w128), w512 = csq2(w256);
  const hc m128 = toh(w128), m256 = toh(w256), m512 = toh(w512);
  {
    const hc m254 = toh(csq2(w127)), m127 = toh(w127);
    hc m[8];
    m[0] = toh(w64); m[1] = m128; m[2] = m256; m[3] = hmul(m127, m256);
    m[4] = m512; m[5] = hmul(m127, m512); m[6] = hmul(m[4], m254); m[7] = hmul(m[5], m254);
    put(m);
    get(M[0], ad.lm[0]);
#pragma unroll
    for (int s = 0; s < 8; s++) {
      const hc z = at(X, s), y = hmulc(z, at(M[0], s));
      A[s][0] = hu(z.r) + zero; A[s][1] = hu(y.r); A[s][2] = hu(z.i) + zero; A[s][3] = hu(y.i);
    }
#pragma unroll
    for (int i = 0; i < 3; i++) get(M[i], ad.lm[i + 1]);
  }
  tile(0, T0);
  const cpx2 w1024 = csq2(w512), we = csq2(w1024);
  {
    hc t[8];
    t[0] = toh(w1024); t[1] = hmul(t[0], m128);
    t[2] = hmul(t[0], m256); t[3] = hmul(t[1], m256);
#pragma unroll
    for (int i = 0; i < 4; i++) t[4 + i] = hmul(t[i], m512);
    put(t); get(X, ad.lb);
  }
  k2048 = (C.a.r * we.a.r + C.a.i * we.a.i + C.b.r * we.b.r + C.b.i * we.b.i) * sc;
#pragma unroll
  for (int j = 1; j < 5; j++) k[j][0] = k[j][1] = k[j][2] = k[j][3] = 0.f;
#pragma unroll
  for (int s = 0; s < 8; s++) {
#pragma unroll
    for (int j = 0; j < 3; j++) {
      const hc y = hmul(at(T0, s), at(M[j], s));
      mma_h(k[1 + j], A[s], hu(y.r), hu(y.i));
    }
    mma_h(k[4], A[s], X[s >> 1][2 * (s & 1)], X[s >> 1][2 * (s & 1) + 1]);
  }
}

__device__ __forceinline__ void build_tables(uint32_t tb, int lane, float (&k)[5][4], float k2048) {
  const int g = lane >> 2, c = lane & 3;
  const uint32_t kc = tb + T_KC + 16;
  {
    const uint32_t a0 = kc + 16 * g + 4 * c, a2 = kc + 2 * (256 + 4 * g + c);
    const uint32_t a3 = kc + 2 * (384 + 2 * g + 64 * (c & 1) + (c >> 1)), a4 = kc + 2 * (512 + g + 32 * c);
#pragma unroll
    for (int r = 0; r < 2; r++) {
      sts32(a0 + 128 * r, pack_bf(k[0][2 * r], k[0][2 * r + 1]));
      sts32(a0 + 128 * r + 256, pack_bf(k[1][2 * r], k[1][2 * r + 1]));
      const uint32_t w2 = pack_bf(k[2][2 * r], k[2][2 * r + 1]);
      const uint32_t w3 = pack_bf(k[3][2 * r], k[3][2 * r + 1]);
      const uint32_t w4 = pack_bf(k[4][2 * r], k[4][2 * r + 1]);
      sts16(a2 + 64 * r, w2); sts16(a2 + 64 * r + 128, w2 >> 16);
      sts16(a3 + 32 * r, w3); sts16(a3 + 32 * r + 64, w3 >> 16);
      sts16(a4 + 16 * r, w4); sts16(a4 + 16 * r + 32, w4 >> 16);
    }
  }
  if (lane == 0) { sts16(kc + 2 * 640, pack_bf(k2048, 0.f)); sts32(kc - 4, 0); }
  __syncwarp();
  const uint32_t td = tb + T_D + 32;
#pragma unroll
  for (int hf = 0; hf < 2; hf++) {
    const uint2 v = lds64(kc + 256 * hf + 8 * lane);
    const uint32_t pv = lds32(kc + 256 * hf + 8 * lane - 4);
    sts128(td + 512 * hf + 16 * lane, __byte_perm(v.x, pv, 0x7610), __byte_perm(v.x, v.x, 0x1032), __byte_perm(v.y, v.x, 0x7610),
           __byte_perm(v.y, v.y, 0x1032));
  }
#pragma unroll
  for (int hf = 0; hf < 2; hf++) {
    const uint32_t v = lds32(kc + 512 + 128 * hf + 4 * lane), nx = lds32(kc + 516 + 128 * hf + 4 * lane);
    uint32_t w0 = __byte_perm(v, v, 0x1010);
    const uint32_t w1 = w0;
    if (hf == 0) { const uint32_t pv = lds32(kc + 508); if (lane == 0) w0 = __byte_perm(v, pv, 0x7610); }
    sts128(td + 1024 + 512 * hf + 16 * lane, w0, w1, __byte_perm(v, v, 0x1032), __byte_perm(nx, v, 0x7610));
  }
  {
    const uint32_t kk = lds16(kc + 2 * 384);
    const uint32_t w = lane < 3 ? (kk | (kk << 16)) : (lane == 3 ? (kk << 16) : 0u);
    if (lane < 24) sts32(td + 4 * (lane < 16 ? 512 + lane : lane - 24), w);
    const uint32_t lo_ = lds16(kc + 2 * 511), le_ = lds16(kc + 2 * 512);
    const uint32_t ja = tb + T_5 + (lane < 16 ? 4 * lane : 256 + 4 * lane);
    sts32(ja, lane == 16 ? (le_ << 16) : 0u);
    sts32(ja + 384, lane == 16 ? (lo_ << 16) : 0u);
    sts32(tb + (lane < 16 ? T_7 : T_9 - 64) + 4 * lane, 0u);
  }
#pragma unroll
  for (int s = 0; s < 2; s++) {
    const uint32_t b = kc + 2 * (s ? 512 : 384) + 8 * lane;
    const uint2 v = lds64(b);
    uint32_t em = lds16(b - 2), e0 = v.x;
    const uint32_t e4 = lds16(b + 8);
    if (lane == 0) { em = 0; e0 = 0; }
    sts64(tb + (s ? T_7 : T_3) + 64 + 8 * lane, __byte_perm(v.x, em, 0x5432), __byte_perm(v.y, v.x, 0x7632));
    sts64(tb + (s ? T_9 : T_5) + 64 + 8 * lane, __byte_perm(v.y, e0, 0x5410), __byte_perm(e4, v.y, 0x5410));
  }
  __syncwarp();
}

__device__ __forceinline__ uint32_t box2w(int lo, int n, int o) {
  return ((unsigned)(o - lo) < (unsigned)n ? 0x3F80u : 0u) | ((unsigned)(o + 1 - lo) < (unsigned)n ? 0x3F800000u : 0u);
}

template <class Done>
__device__ __forceinline__ void dense_block(int be, bool init, bool more, uint32_t qa, uint32_t st, const uint32_t (&F)[66],
                                            uint32_t (&qd)[8][4], float (&T)[5][4], float (&ci)[4], Done done) {
  const uint32_t qp = qa + 128 * be;
  uint2 sv;
#pragma unroll
  for (int k = 4; k >= 1; k--) mmac(T[k], qd[0][0], qd[0][1], qd[0][2], qd[0][3], F[16 * k + 1], F[16 * k], T[k - 1]);
  if (init) mmac(T[0], qd[0][0], qd[0][1], qd[0][2], qd[0][3], F[1], F[0], ci);
  else mma0(T[0][0], T[0][1], T[0][2], T[0][3], qd[0][0], qd[0][1], qd[0][2], qd[0][3], F[1], F[0]);
  ldsm4(qd[6], qp - 16 * 6);
  ldsm4(qd[7], qp - 16 * 7);
  if (init && more) sv = lds64(st + 256 * (be - 1));
#pragma unroll
  for (int i = 1; i < 8; i++) {
#pragma unroll
    for (int k = 3; k >= 0; k--)
      mma(T[k][0], T[k][1], T[k][2], T[k][3], qd[i][0], qd[i][1], qd[i][2], qd[i][3], F[16 * k + 2 * i + 1], F[16 * k + 2 * i]);
    if (i < 7 && more) ldsm4(qd[i - 1], qp - 128 - 16 * (i - 1));
    if (i == 2) done(pack_bf(T[4][0], T[4][1]), pack_bf(T[4][2], T[4][3]));
    if (i == 4 && init && more) { ci[0] = bf_lo(sv.x); ci[1] = bf_hi(sv.x); ci[2] = bf_lo(sv.y); ci[3] = bf_hi(sv.y); }
  }
}
__device__ __forceinline__ uint32_t quad_addr(uint32_t ub, int lane) {
  const int mi = lane >> 3;
  return ub + U_PAD + 16 * (lane & 7) + ((mi == 0 || mi == 3) ? U_ODD : 0) - (mi == 0 ? 16 : 0);
}
__device__ __forceinline__ void store_pairs(uint4* ydst, const float (&T)[5][4]) {
#pragma unroll
  for (int B = 1; B >= 0; B--)
    st_x(ydst + B * 32, nz(pack_bf(T[2 * B][0], T[2 * B][1])), pack_bf(T[2 * B][2], T[2 * B][3]),
         pack_bf(T[2 * B + 1][0], T[2 * B + 1][1]), pack_bf(T[2 * B + 1][2], T[2 * B + 1][3]));
}
__device__ __forceinline__ void conv_helper(uint32_t ub, uint32_t tb, int lane, uint4* ydst) {
  const uint32_t qa = quad_addr(ub, lane), st = tb + T_ST + lane * 8, fa = tb + T_D + 32 + 4 * ((lane >> 2) - 2 * (lane & 3));
  uint32_t F[66], qd[8][4];
#pragma unroll
  for (int i = 0; i < 6; i++) ldsm4(qd[i], qa + 128 * 3 - 16 * i);
#pragma unroll
  for (int m = 0; m < 66; m++) F[(m & 1) + 16 * ((m >> 1) & 3) + 2 * (m >> 3) + (m >= 64 ? 48 : 0)] = lds32(fa + 32 * ((m & 1) + 16 * ((m >> 1) & 3) + 2 * (m >> 3) + (m >= 64 ? 48 : 0)));
  float T[5][4], ci[4];
#pragma unroll
  for (int i = 0; i < 20; i++) T[i >> 2][i & 3] = 0.f;
#pragma unroll
  for (int be = 3; be >= 0; be--) {
    if (be == 1) SPLIT();
    dense_block(be, false, be > 0, qa, st, F, qd, T, ci, [&](uint32_t w0, uint32_t w1) { sts64(st + 256 * (12 + be), w0, w1); });
  }
  nb_arrive(NB_HELP, 256);
  store_pairs(ydst, T);
}

__device__ __forceinline__ void conv_channel(uint32_t ub, uint32_t tb, int lane, uint4* ydst) {
  const int g = lane >> 2, c = lane & 3, x = g - 2 * c;
  const int mi = lane >> 3;
  const uint32_t qa = quad_addr(ub, lane);
  const uint32_t hb = ub + U_PAD + (mi & 1) * U_ODD + 16 * ((lane >> 4) + (lane & 7)) - 16;
  const uint32_t kv = lds16(tb + T_KC + 16 + 2 * 512);
  const int oh = c < 2 ? 8 + 2 * c : 2 * c - 8, og = c < 3 ? 2 * c : -10;
  uint32_t bx[4] = {box2w(g - 4, 9, 2 * c), box2w(g - 3, 7, 2 * c), box2w(g - 4, 9, oh), box2w(g - 3, 7, oh)};
  uint32_t by[4] = {box2w(g - 10, 5, 2 * c - 8), box2w(g - 5, 3, 2 * c - 8), box2w(g - 10, 5, og), box2w(g - 5, 3, og)};
  uint32_t lb0 = ((unsigned)(x + 5) < 2u ? kv : 0u) | ((unsigned)(x + 4) < 2u ? kv << 16 : 0u);
  uint32_t lb1 = ((unsigned)(x - 3) < 2u ? kv : 0u) | ((unsigned)(x - 4) < 2u ? kv << 16 : 0u);
  const int q0 = g - 1, q1 = c < 3 ? g : g - 2;
  uint32_t y0a = ub + U_PAD + (q0 & 1) * U_ODD + 16 * (q0 >> 1) + 4 * c;
  uint32_t y1a = ub + U_PAD + (q1 & 1) * U_ODD + 16 * (q1 >> 1) + 4 * c;
#pragma unroll
  for (int i = 0; i < 4; i++) asm volatile("" : "+r"(bx[i]), "+r"(by[i]));
  asm volatile("" : "+r"(lb0), "+r"(lb1), "+r"(y0a), "+r"(y1a));
  nb_arrive(NB_YZ0, 288);
  mbar_wait(BAR(MB_UFULL));
  mbar_spin(BAR(MB_EMPTY + 15));
  TS(36);
  float acc[16][4];
  {
    uint32_t z09[8], z07[8], zm9[8], zm7[8];
#pragma unroll
    for (int i = 0; i < 8; i++) {
      uint32_t h[4];
      ldsm4(h, hb + 128 * i);
      float y0, y1, y2, y3, w0, w1, w2, w3;
      mma0(y0, y1, y2, y3, bx[0], bx[1], bx[2], bx[3], h[2], c < 2 ? h[3] : h[1]);
      mma0(w0, w1, w2, w3, bx[0], bx[1], bx[2], bx[3], h[1], c < 2 ? h[2] : h[0]);
      z09[i] = pack_bf(y0, y1); z07[i] = pack_bf(y2, y3);
      zm9[i] = pack_bf(w0, w1); zm7[i] = pack_bf(w2, w3);
    }
  uint32_t f3[3][4][4];
  {
    const uint32_t fa = tb + T_7 + 4 * (16 + x);
#pragma unroll
    for (int tt = 0; tt < 3; tt++)
#pragma unroll
      for (int D = 0; D < 4; D++) {
        const uint32_t a = fa + (tt == 0 ? 316 : (tt == 1 ? 320 : 0)) + 64 * D;
        f3[tt][D][0] = lds32(a); f3[tt][D][1] = lds32(a + 32); f3[tt][D][2] = lds32(a - 32); f3[tt][D][3] = lds32(a);
      }
  }
    SPLIT();
    nb_sync(NB_GATE, 256);
    SPLIT();
    float a[4][2][4];
#pragma unroll
    for (int kap = 0; kap < 4; kap++)
#pragma unroll
      for (int sg = 0; sg < 2; sg++)
#pragma unroll
        for (int bk = 3; bk >= kap; bk--) {
          const uint32_t(&q0_)[4] = f3[sg ? 2 : 0][bk - kap];
          const uint32_t(&q1_)[4] = f3[sg ? 2 : 1][bk - kap];
          float(&a0)[4] = a[bk][0];
          float(&a1)[4] = a[bk][1];
          if (sg == 0 && kap == 0) {
            mma0(a0[0], a0[1], a0[2], a0[3], q0_[0], q0_[1], q0_[2], q0_[3], z09[0], z09[1]);
            mma0(a1[0], a1[1], a1[2], a1[3], q1_[0], q1_[1], q1_[2], q1_[3], zm9[0], zm9[1]);
          } else {
            mma(a0[0], a0[1], a0[2], a0[3], q0_[0], q0_[1], q0_[2], q0_[3], sg ? zm7[2 * kap] : z09[2 * kap], sg ? zm7[2 * kap + 1] : z09[2 * kap + 1]);
            mma(a1[0], a1[1], a1[2], a1[3], q1_[0], q1_[1], q1_[2], q1_[3], sg ? z07[2 * kap] : zm9[2 * kap], sg ? z07[2 * kap + 1] : zm9[2 * kap + 1]);
          }
        }
    SPLIT();
#pragma unroll
    for (int i = 0; i < 8; i++) {
      uint32_t h[4];
      ldsm4(h, qa + 128 * i);
      const float ci[4] = {a[i >> 1][0][2 * (i & 1)], a[i >> 1][0][2 * (i & 1) + 1], a[i >> 1][1][2 * (i & 1)], a[i >> 1][1][2 * (i & 1) + 1]};
      mmac(acc[8 + i], h[0], h[1], h[2], h[3], lb0, lb1, ci);
    }
  }
  TS(44);
  {
    uint2 a5[10], a3[10];
    const uint32_t aa = tb + T_5 + 4 * (8 + 2 * g - 2 * c);
#pragma unroll
    for (int m = 0; m < 10; m++) { a5[m] = lds64(aa + 32 * m); a3[m] = lds64(aa + 384 + 32 * m); }
    uint32_t x5[12][2], x3[12][2];
    auto ygen = [&](int kap) {
#pragma unroll
      for (int hh = 0; hh < 2; hh++) {
        float y0, y1, y2, y3;
        mma0(y0, y1, y2, y3, by[0], by[1], by[2], by[3], lds32(y0a + 128 * kap + 64 * hh), lds32(y1a + 128 * kap + 64 * hh));
        x5[kap][hh] = pack_bf(y0, y1);
        x3[kap][hh] = pack_bf(y2, y3);
      }
    };
    ygen(11); ygen(10); ygen(9); ygen(8);
#pragma unroll
    for (int kap = 11; kap >= 0; kap--) {
      if (kap >= 4) ygen(kap - 4);
#pragma unroll
      for (int sg = 0; sg < 2; sg++)
#pragma unroll
        for (int i = 4; i >= 0; i--) {
          const int be = kap + 4 + i;
          if (be <= 15) {
            const uint2 &hi = sg ? a3[2 * i + 1] : a5[2 * i + 1], &lo = sg ? a3[2 * i] : a5[2 * i];
            const uint32_t b0 = sg ? x3[kap][0] : x5[kap][0], b1 = sg ? x3[kap][1] : x5[kap][1];
            if (be < 8 && i == 0 && sg == 0) mma0(acc[be][0], acc[be][1], acc[be][2], acc[be][3], hi.x, hi.y, lo.x, lo.y, b0, b1);
            else mma(acc[be][0], acc[be][1], acc[be][2], acc[be][3], hi.x, hi.y, lo.x, lo.y, b0, b1);
          }
        }
    }
  }
  TS(45);
  {
    const uint32_t st = tb + T_ST + lane * 8;
#pragma unroll
    for (int be = 4; be < 12; be++) sts64(st + 256 * be, pack_bf(acc[be][0], acc[be][1]), pack_bf(acc[be][2], acc[be][3]));
    SPLIT();
    uint32_t F[66], qd[8][4];
    const uint32_t fa = tb + T_D + 32 + 4 * x;
#pragma unroll
    for (int i = 0; i < 32; i++) {
      const int s = 120 - (i >> 2) - 8 * (i & 3);
      uint32_t(&q)[4] = qd[i & 7];
      ldsm4(q, qa + 16 * s);
      const int m = 16 * (i & 3) + 2 * (i >> 2);
      F[m] = lds32(fa + 32 * m); F[m + 1] = lds32(fa + 32 * m + 32);
#pragma unroll
      for (int be = 15; be >= 12; be--) {
        const int de = 8 * be - s;
        float(&a)[4] = (be >= 14 && !(i & 1)) ? acc[be - 4] : acc[be];
        if (de >= 0 && be >= 14 && i == 2 * (15 - be)) mma0(a[0], a[1], a[2], a[3], q[0], q[1], q[2], q[3], F[2 * de + 1], F[2 * de]);
        else if (de >= 0) mma(a[0], a[1], a[2], a[3], q[0], q[1], q[2], q[3], F[2 * de + 1], F[2 * de]);
      }
    }
#pragma unroll
    for (int i = 0; i < 8; i++) acc[14 + (i >> 2)][i & 3] += acc[10 + (i >> 2)][i & 3];
    F[64] = lds32(fa + 32 * 64); F[65] = lds32(fa + 32 * 65);
#pragma unroll
    for (int i = 0; i < 6; i++) ldsm4(qd[i], qa + 128 * 11 - 16 * i);
    uint2 sv = lds64(st + 256 * 11);
    float ci[4] = {bf_lo(sv.x), bf_hi(sv.x), bf_lo(sv.y), bf_hi(sv.y)};
    float T[5][4];
#pragma unroll
    for (int i = 0; i < 16; i++) T[i >> 2][i & 3] = acc[12 + (i >> 2)][i & 3];
    nb_sync(NB_YZ, 160);
    TS(46);
    uint32_t held[2];
#pragma unroll
    for (int be = 11; be >= 4; be--) {
      if (be & 1) SPLITN(be);
      dense_block(be, true, be > 4, qa, st, F, qd, T, ci, [&](uint32_t w0, uint32_t w1) {
        if (be & 1) { held[0] = w0; held[1] = w1; }
        else st_x(ydst + (be + 4) * 16, nz(w0), w1, held[0], held[1]);
        if (be == 7) nb_arrive(NB_Y + 3, 160);
      });
    }
    nb_arrive(NB_Y + 2, 160);
    nb_sync(NB_HELP, 256);
#pragma unroll
    for (int k = 0; k < 4; k++) {
      const uint2 v = lds64(st + 256 * (12 + k));
      T[k][0] += bf_lo(v.x); T[k][1] += bf_hi(v.x); T[k][2] += bf_lo(v.y); T[k][3] += bf_hi(v.y);
    }
    store_pairs(ydst + 64, T);
  }
}

__device__ __forceinline__ void dual_exp(const uint32_t* w, uint32_t* e) {
  const float L = 1.44268798828125f;
  uint32_t mx = bmax2(bmax2(w[0], w[1]), bmax2(w[2], w[3]));
  uint32_t mn = bmin2(bmin2(w[0], w[1]), bmin2(w[2], w[3]));
  mx = bmax2(mx, __shfl_xor_sync(0xffffffffu, mx, 1));
  mn = bmin2(mn, __shfl_xor_sync(0xffffffffu, mn, 1));
  mx = bmax2(mx, __shfl_xor_sync(0xffffffffu, mx, 2));
  mn = bmin2(mn, __shfl_xor_sync(0xffffffffu, mn, 2));
  const float mx0 = bf_lo(mx) * -L, mx1 = bf_hi(mx) * -L, mn0 = bf_lo(mn) * L, mn1 = bf_hi(mn) * L;
#pragma unroll
  for (int i = 0; i < 2; i++) {
    const float a0 = bf_lo(w[2 * i]), a1 = bf_hi(w[2 * i]), b0 = bf_lo(w[2 * i + 1]), b1 = bf_hi(w[2 * i + 1]);
    e[2 * i] = pack_bf(ex2(fmaf(a0, L, mx0)), ex2(fmaf(b0, L, mx0)));
    e[2 * i + 1] = pack_bf(ex2(fmaf(a1, L, mx1)), ex2(fmaf(b1, L, mx1)));
    e[4 + 2 * i] = pack_bf(ex2(fmaf(a0, -L, mn0)), ex2(fmaf(b0, -L, mn0)));
    e[5 + 2 * i] = pack_bf(ex2(fmaf(a1, -L, mn1)), ex2(fmaf(b1, -L, mn1)));
  }
}
__device__ __forceinline__ void normalise(uint32_t* e, const float (&s)[4]) {
  const uint32_t r = pack_bf(rcp(s[0]), rcp(s[2]));
  const __nv_bfloat162 rr = *(const __nv_bfloat162*)&r;
#pragma unroll
  for (int i = 0; i < 4; i++) {
    const __nv_bfloat162 v = __hmul2(*(const __nv_bfloat162*)&e[i], (i & 1) ? __high2bfloat162(rr) : __low2bfloat162(rr));
    e[i] = *(const uint32_t*)&v;
  }
}
__host__ __device__ constexpr uint64_t qdesc(uint32_t addr) { return mkdesc(addr, 128, 256, 0); }

__global__ void __launch_bounds__(NTHREADS, 1)
fused_kernel(const Params P, const __grid_constant__ CUtensorMap mx, const __grid_constant__ CUtensorMap mw,
             const __grid_constant__ CUtensorMap mo, const __grid_constant__ CUtensorMap mu,
             const __grid_constant__ CUtensorMap mout) {
  constexpr uint32_t sb = SB;
  const int tid = threadIdx.x, lane = tid & 31;
  const int warp = __shfl_sync(0xffffffffu, tid >> 5, 0);
  const int b = blockIdx.x, oct = b >> 3, i8 = b & 7;
  const int rt = (((oct & 4) ? ~oct : oct) & 3) * 2 + (i8 >> 2);
  const int hp = (oct >> 2) * 4 + (i8 & 3);

  const int wg = warp >> 2, w = warp & 3;
  const int d = b * 4 + ((tid >> 5) & 3);
  const KgenRaw raw = kgen_load(P, d, (tid >> 7) & 1, lane, (tid + 128) & 256);
  const uint32_t tb = sb + OFF_T + w * T_CH;
  if (warp >= 12) {
    asm volatile("setmaxnreg.dec.sync.aligned.u32 32;");
    if (warp == 12) {
      if (lane == 0) {
#pragma unroll
        for (int i = 0; i < 9; i++) mbar_init(BAR(i), 1);
        asm volatile("fence.mbarrier_init.release.cluster;" ::: "memory");
      }
      __syncwarp();
      if (lane < 9) mbar_expect(BAR(0) + 8 * lane, lane == 0 ? 16384 : 28672);
      __syncwarp();
      nb_arrive(NB_PROD, 384);
#pragma unroll 1
      for (int kb = 0; kb < 8; kb++) {
        if (kb == U_AT) e_tma4d(sb + OFF_STG0, &mu, BAR(MB_URAW), i8 * 64, oct * 2);
        e_tma3d(sb + OFF_W + kb * 12288, &mw, BAR(MB_FULL) + 8 * kb, hp * 32, kb * 64, 0);
        if (kb < 5) e_tma2d(sb + OFF_X + (kb < 2 ? kb + 3 : kb - 2) * 16384, &mx, BAR(MB_FULL) + 8 * kb, kb * 64, rt * 256);
      }
      if (smem_u32(smem_raw) != SB) __trap();
      if (lane == 0) TS1(54);
      nb_sync(NB_GATE + 1, 64);
      e_prefetch(P.x + (size_t)(rt * 256 + 128 + hp * 8) * 512, 8192);
      uint32_t slot = sb + OFF_X + 3 * 16384;
#pragma unroll 1
      for (int n = 0; n < 11; n++) {
        mbar_spin(BAR(MB_EMPTY) + 8 * n);
        const int m = n + 5;
        e_tma2d(slot, &mx, BAR(MB_FULL) + 8 * m, (m & 7) * 64, rt * 256 + (m >> 3) * 128);
        slot = slot == sb + OFF_X + 4 * 16384 ? sb + OFF_X : slot + 16384;
        if (n == 7) {
          e_prefetch(P.wo + (size_t)b * 2048, 4096);
          asm volatile("prefetch.tensormap [%0];" ::"l"(&mo) : "memory");
          asm volatile("prefetch.tensormap [%0];" ::"l"(&mout) : "memory");
        }
      }
#pragma unroll 1
      for (int i = 0; i < 8; i++) {
        mbar_wait(BAR(MB_EMPTY + 10) + 8 * ((0x54332222u >> (4 * i)) & 7));
        const int w0 = (0x54736210u >> (4 * i)) & 7;
        e_tma3d(sb + OFF_W + w0 * 16384, &mo, BAR(MB_WO), 0, w0 * 64, (hp & 3) * 2);
      }
    } else {
      if (warp == 13) {
        if (lane == 0) {
#pragma unroll
          for (int i = 9; i < 40; i++) mbar_init(BAR(i), i < MB_EMPTY ? 1 : 4);
          asm volatile("fence.mbarrier_init.release.cluster;" ::: "memory");
        }
        __syncwarp();
        if (lane < 14 && lane != 9) mbar_expect(BAR(MB_FULL + 8) + 8 * lane, lane == 8 ? 131072 : (lane == 10 ? 8192 : (lane == 13 ? 24576 : 16384)));
        nb_arrive(NB_GATE + 1, 64);
      } else if (warp == 14) {
        asm volatile("prefetch.tensormap [%0];" ::"l"(&mw) : "memory");
        asm volatile("prefetch.tensormap [%0];" ::"l"(&mx) : "memory");
        asm volatile("prefetch.tensormap [%0];" ::"l"(&mu) : "memory");
        e_prefetch(P.x + (size_t)(rt * 256 + hp * 8) * 512, 8192);
      }
      nb_sync(NB_PROD, 384);
      if (warp == 15) {
        const uint4 v0 = __ldg((const uint4*)P.wphi + hp * 64 + lane), v1 = __ldg((const uint4*)P.wphi + hp * 64 + 32 + lane);
        sts128(sb + OFF_PHI + (lane & 1) * 256 + (lane >> 1) * 16, v0.x, v0.y, v0.z, v0.w);
        sts128(sb + OFF_PHI + 512 + (lane & 1) * 256 + (lane >> 1) * 16, v1.x, v1.y, v1.z, v1.w);
        const uint32_t one = (((lane >> 3) ^ (lane >> 4)) & 1) ? 0u : ((lane & 1) ? 0x3F800000u : 0x3F80u);
        const int q = (lane >> 1) & 3;
        sts128(sb + OFF_EYE + lane * 16, q == 0 ? one : 0u, q == 1 ? one : 0u, q == 2 ? one : 0u, q == 3 ? one : 0u);
        sts64(sb + OFF_ONE + lane * 8, 0x3F803F80u, 0x3F803F80u);
        asm volatile("fence.proxy.async.shared::cta;" ::: "memory");
        nb_arrive(NB_KREAD, 160);
      }
      uint32_t* cnt = (uint32_t*)(P.xs + X_CNT) + (warp == 13 ? i8 : (warp == 14 ? 8 + rt : 16 + oct)) * 32;
      const unsigned target = (ld_x32(cnt) & ~15u) + 16;
      if (warp != 14) {
        if (warp == 15) mbar_wait(BAR(MB_EMPTY + ZERO_STEP));
        uint4* pz = P.xs + (warp == 13 ? X_PART + (hp * 8 + rt) * 144 : X_Y + b * 1024) + lane;
#pragma unroll 1
        for (int i = (warp == 13 ? 144 : 1024) - lane; i > 0; i -= 32, pz += 32) st_x(pz, 0, 0, 0, 0);
      }
      if (warp == 15) __syncwarp();
      else nb_sync(warp == 13 ? NB_INIT : NB_ODONE, warp == 13 ? 160 : 288);
      if (lane == 0) asm volatile("red.release.gpu.global.add.u32 [%0], %1;" ::"l"(cnt), "r"(warp == 15 ? 2 : 1) : "memory");
      if (lane == 0) TS1(warp == 13 ? 50 : (warp == 14 ? 57 : 53));
      __syncwarp();
      if (warp == 14) nb_arrive(NB_GATE + 1, 160);
      asm volatile("fence.proxy.async.shared::cta;" ::: "memory");
      if (warp == 13) cnt += ((lane & 1 ? b >> 4 : i8 ^ (lane & 4)) - i8) * 32;
#pragma unroll 1
      for (int i = 0; i < SPIN_MAX; i++) {
        unsigned v;
        asm volatile("ld.acquire.gpu.global.u32 %0, [%1];" : "=r"(v) : "l"(cnt) : "memory");
        if (__all_sync(0xffffffffu, (int)(v - target) >= 0)) break;
      }
      if (lane == 0) TS1(warp == 13 ? 51 : (warp == 14 ? 58 : 55));
      if (warp == 15) { nb_arrive(NB_YZ, 160); nb_arrive(NB_YZ0, 288); return; }
      asm volatile("fence.proxy.async.global;" ::: "memory");
      if (warp == 13) {
        mbar_wait(BAR(MB_EMPTY + 11));
        e_expect(BAR(MB_UFULL), 4 * U_CH);
        e_bulk(sb + OFF_U, P.xs + X_UT + b * (U_CH / 4), 4 * U_CH, BAR(MB_UFULL));
      } else {
        const uint4* src = P.xs + X_O + (rt * 4 + (hp >> 2)) * 4096;
        e_bulk(sb + OFF_X + 32768 + 57344, src + 3584, 8192, BAR(MB_O));
        e_bulk(sb + OFF_X + 32768, src, 16384, BAR(MB_O + 1));
        e_bulk(sb + OFF_X + 49152, src + 1024, 16384, BAR(MB_O + 2));
        e_bulk(sb + OFF_STG0, src + 3200, 6144, BAR(MB_O + 3));
        nb_sync(NB_BDONE, 288);
        asm volatile("fence.proxy.async.shared::cta;" ::: "memory");
        e_bulk(sb + OFF_U, src + 2048, 18432, BAR(MB_O + 3));
      }
    }
    return;
  }

  asm volatile("setmaxnreg.inc.sync.aligned.u32 160;");
  const int t = tid & 127;
  const int g = lane >> 2, c = lane & 3;
  const uint32_t kp = ((tb + 127) & ~127u) + (wg & 1) * 2048;
  const KgenAddr kad = kgen_addr(lane, kp);
  if (wg) nb_sync(NB_PROD, 384);
  float k[5][4], k2048, ksc;
  if (wg) {
    kgen_unit(raw, kad, blockIdx.y, k, k2048, ksc);
    TS(40 + wg);
    if ((fu(k[0][0]) & fu(k[1][0]) & fu(k[2][0]) & fu(k[3][0]) & fu(k[4][0])) == 0xffffffffu) sts32(kp, 0);
  }
  if (wg) nb_arrive(0, 384);
  if (wg) {
    if (wg == 1) {
      uint32_t h[10];
#pragma unroll
      for (int j = 0; j < 10; j++) h[j] = hu(__floats2half2_rn(k[j >> 1][2 * (j & 1)], k[j >> 1][2 * (j & 1) + 1]));
      sts128(kp + lane * 16, h[0], h[1], h[2], h[3]);
      sts128(kp + 512 + lane * 16, h[4], h[5], h[6], h[7]);
      sts128(kp + 1024 + lane * 16, h[8], h[9], fu(k2048), fu(ksc));
      nb_arrive(NB_PREP, 256);
    }
  } else {
    nb_sync(NB_KREAD, 160);
    nb_sync(0, 384);
  }
  if (wg == 1) {
    mbar_wait(BAR(MB_URAW));
    TS(48);
    uint4* dst = P.xs + X_UT + (i8 * 64 + g) * (U_CH / 16) + (w & 1) * (U_ODD / 16) + U_PAD / 16 + oct * 8 + (w >> 1) * 4 + c;
    const int ln = ((lane >> 1) & 3) + 4 * (lane & 1);
    uint32_t r[8][4];
#pragma unroll
    for (int i = 0; i < 8; i++) ldsm4t(r[i], sb + OFF_STG0 + w * 4096 + ((lane >> 3) * 8 + ln) * 128 + ((i ^ ln) << 4));
#pragma unroll
    for (int i = 0; i < 8; i++) dst[i * (U_CH / 2)] = make_uint4(r[i][0], r[i][1], r[i][2], r[i][3]);
    nb_arrive(NB_INIT, 160);
    if (lane == 0) mbar_arrive(BAR(MB_AUX));
  }
  {
    if (wg == 2) {
#pragma unroll
      for (int j = 0; j < 5; j++) { k[j][0] *= ksc; k[j][1] *= ksc; k[j][2] *= ksc; k[j][3] *= ksc; }
      const unsigned short dsk = __ldg((const unsigned short*)P.Dskip + d);
      nb_sync(NB_PREP, 256);
      {
        const uint32_t src = kp + 2048 + lane * 16;
        const uint4 v0 = lds128(src), v1 = lds128(src + 512), v2 = lds128(src + 1024);
        const uint32_t h[10] = {v0.x, v0.y, v0.z, v0.w, v1.x, v1.y, v1.z, v1.w, v2.x, v2.y};
#pragma unroll
        for (int j = 0; j < 10; j++) {
          const float2 f = __half22float2(*(const __half2*)&h[j]);
          k[j >> 1][2 * (j & 1)] = fmaf(f.x, uf(v2.w), k[j >> 1][2 * (j & 1)]);
          k[j >> 1][2 * (j & 1) + 1] = fmaf(f.y, uf(v2.w), k[j >> 1][2 * (j & 1) + 1]);
        }
        k2048 += uf(v2.z);
      }
#pragma unroll
      for (int o2 = 16; o2; o2 >>= 1) k2048 += __shfl_xor_sync(0xffffffffu, k2048, o2);
      if (lane == 0) k[0][0] += bf_lo(dsk);
      __syncwarp();
      TS(34);
      build_tables(tb, lane, k, k2048);
      TS(35);
      uint4* const g_y = P.xs + X_Y;
      conv_channel(sb + OFF_U + w * U_CH, tb, lane, g_y + (size_t)d * 256 + lane);
      nb_arrive(NB_BDONE, 288);
      nb_arrive(NB_Y + 1, 160);
      TS(37);
      if (w == 0) TSDUMP(32);
      return;
    }
    if (wg == 1) {
      mbar_wait(BAR(MB_EMPTY + 4));
      mbar_spin(BAR(MB_EMPTY + 6));
    }
    TS(wg * 16 + 1);
  }

  float acc[2][48];
  {
    uint32_t fb = BAR(MB_FULL) + 64 * wg;
    uint32_t da = (uint32_t)mkdesc(sb + OFF_X, 16, 0, 0) + (wg ? 1024 : 3072), db = (uint32_t)mkdesc(sb + OFF_W, 4096, 0, 0);
    constexpr uint64_t ha = mkdesc(0, 0, 1024, 1), hb = mkdesc(0, 0, 512, 2);
    mbar_spin(fb);
    TS(wg * 16 + 2);
#pragma unroll 1
    for (int kb = 0; kb < 8; kb++) {
      WG_FENCE();
#pragma unroll
      for (int k = 0; k < 4; k++) {
        wgmma_ss_n96(acc[0], ha | (da + 2 * k), hb | (db + 64 * k), k ? 1 : kb);
        wgmma_ss_n96(acc[1], ha | (da + 2 * k + 512), hb | (db + 64 * k), k ? 1 : kb);
      }
      WG_COMMIT();
      if (kb < 7) mbar_spin(fb + 8);
      WG_WAIT(1);
      if (kb > 0) e_arrive(fb + 8 * (MB_EMPTY - MB_FULL - 1));
      fb += 8; db += 768;
      da = da == (uint32_t)mkdesc(sb + OFF_X + 65536, 16, 0, 0) ? da - 4096 : da + 1024;
    }
    WG_WAIT(0);
    e_arrive(fb + 8 * (MB_EMPTY - MB_FULL - 1));
    SPLIT();
  }
  TS(wg * 16 + 3);

  constexpr uint32_t stg0 = sb + OFF_STG0, stg1 = sb + OFF_X + 32768;
  uint4* const g_part = P.xs + X_PART;
  uint4* const g_o = P.xs + X_O;
  constexpr uint32_t kvs = stg0;
  auto pack8 = [](const float* a) { return make_uint4(pack_bf(a[0], a[1]), pack_bf(a[2], a[3]), pack_bf(a[4], a[5]), pack_bf(a[6], a[7])); };
  auto stage_k = [&](auto nt, const uint4* af, const uint4* vp, uint32_t sl, uint32_t free_bar) {
    constexpr int NU = 2 * decltype(nt)::value;
    float p[NU][8], rs[2 * NU][4];
    uint32_t ek[8 * NU];
    WG_FENCE();
#pragma unroll
    for (int u = 0; u < NU; u++) wgmma_rs_n16(p[u], af[u], qdesc(sb + OFF_PHI + (u & 1) * 512), 0);
    WG_COMMIT();
    WG_WAIT(0);
#pragma unroll
    for (int u = 0; u < NU; u++) {
      const uint32_t pw[4] = {pack_bf(p[u][0], p[u][2]), pack_bf(p[u][1], p[u][3]), pack_bf(p[u][4], p[u][6]), pack_bf(p[u][5], p[u][7])};
      dual_exp(pw, ek + 8 * u);
    }
    TS(wg * 16 + 12);
    mbar_spin(free_bar);
    WG_FENCE();
#pragma unroll
    for (int i = 0; i < 2 * NU; i++) wgmma_rs_n8(rs[i], make_uint4(ek[4 * i], ek[4 * i + 1], ek[4 * i + 2], ek[4 * i + 3]), qdesc(sb + OFF_ONE), 0);
    WG_COMMIT();
#pragma unroll
    for (int i = 0; i < NU; i++) stsm4(sl + (i >> 1) * 4 * SLAB + 2048 + (i & 1) * 512, vp[i].x, vp[i].y, vp[i].z, vp[i].w);
    if (NU == 4 || lane < 16) sts128(sl + (lane >> 4) * (4 * SLAB - 256) + 3072, 0x3F803F80u, 0x3F803F80u, 0x3F803F80u, 0x3F803F80u);
    WG_WAIT(0);
#pragma unroll
    for (int i = 0; i < 2 * NU; i++) {
      normalise(ek + 4 * i, rs[i]);
      stsm4(sl + (i >> 2) * 4 * SLAB + (i & 3) * 512, ek[4 * i], ek[4 * i + 1], ek[4 * i + 2], ek[4 * i + 3]);
    }
    asm volatile("fence.proxy.async.shared::cta;" ::: "memory");
  };
  auto contract = [&](float (&kc)[20], uint32_t stg, int acc_in) {
    WG_FENCE();
#pragma unroll
    for (int s = 0; s < 8; s++) wgmma_ss_n40(kc, qdesc(stg + s * SLAB), qdesc(stg + s * SLAB + 2048), s ? 1 : acc_in);
    WG_COMMIT();
    WG_WAIT(0);
  };
  uint32_t eq[32];
  {
    uint4 af[4], aq[4], vp[4];
    float kc[20];
#pragma unroll
    for (int u = 0; u < 4; u++) { af[u] = pack8(acc[u >> 1] + 16 + 8 * (u & 1)); vp[u] = pack8(acc[u >> 1] + 32 + 8 * (u & 1)); }
    const uint32_t hand = stg1 + 16384 + 8192 + w * 2048 + lane * 16;
    if (wg) {
      sts128(hand, af[2].x, af[2].y, af[2].z, af[2].w); sts128(hand + 512, af[3].x, af[3].y, af[3].z, af[3].w);
      sts128(hand + 1024, vp[2].x, vp[2].y, vp[2].z, vp[2].w); sts128(hand + 1536, vp[3].x, vp[3].y, vp[3].z, vp[3].w);
      nb_arrive(NB_HAND, 256);
    }
#pragma unroll
    for (int u = 0; u < 4; u++) aq[u] = pack8(acc[u >> 1] + 8 * (u & 1));
    if (wg == 0) {
      stage_k(std::integral_constant<int, 2>(), af, vp, stg0 + w * SLAB + lane * 16, BAR(MB_AUX));
      TS(13);
      nb_sync(NB_WG0, 128);
      contract(kc, stg0, 0);
      mbar_wait(BAR(MB_UFULL));
      TS(15);
      nb_sync(NB_HAND, 256);
      af[0] = lds128(hand); af[1] = lds128(hand + 512); vp[0] = lds128(hand + 1024); vp[1] = lds128(hand + 1536);
      nb_sync(NB_WG0, 128);
    }
    stage_k(std::integral_constant<int, 1>(), af, vp, stg1 + (wg ? w : 4 + w) * SLAB + lane * 16, BAR(MB_EMPTY + 15));
    TS(wg * 16 + 14);
    float p[4][8];
    if (wg) {
      nb_arrive(NB_ST0, 256);
      nb_arrive(NB_GATE, 256);
    } else {
      uint4* pp = g_part + (size_t)(hp * 8 + rt) * 144 + t;
      uint32_t* pz = (uint32_t*)(pp - t + 128) + w * 16 + c * 8 + g;
      asm volatile("" : "+l"(pp), "+l"(pz));
      nb_sync(NB_ST0, 256);
      contract(kc, stg1, 1);
      TS(6);
      float kv[8];
#pragma unroll
      for (int i = 0; i < 8; i++) kv[i] = w & 2 ? kc[8 + i] : kc[i];
      st_x(pp, nz(pack_bf(kv[0], kv[1])), pack_bf(kv[2], kv[3]), pack_bf(kv[4], kv[5]), pack_bf(kv[6], kv[7]));
      if (c < 2) st_x32(pz, nz(fu(c ? kc[18] : kc[16])));
      TS(5);
    }
    SPLIT();
    WG_FENCE();
#pragma unroll
    for (int u = 0; u < 4; u++) wgmma_rs_n16(p[u], aq[u], qdesc(sb + OFF_PHI + (u & 1) * 512), 0);
    WG_COMMIT();
    WG_WAIT(0);
#pragma unroll
    for (int u = 0; u < 4; u++) {
      const uint32_t pw[4] = {pack_bf(p[u][0], p[u][2]), pack_bf(p[u][1], p[u][3]), pack_bf(p[u][4], p[u][6]), pack_bf(p[u][5], p[u][7])};
      dual_exp(pw, eq + 8 * u);
    }
    SPLIT();
  }
  TS(wg * 16 + 4);
  if (wg == 1) {
    mbar_wait(BAR(MB_UFULL));
    const uint4* ps = g_part + (size_t)hp * 8 * 144 + t;
    const uint32_t* zs = (const uint32_t*)(g_part + (size_t)(hp * 8 + (lane >> 4) * 4) * 144 + 128) + w * 16 + (lane & 15);
    uint4 v[8];
    uint32_t zv[4];
#pragma unroll 1
    for (int it = 0; it < SPIN_MAX; it++) {
#pragma unroll
      for (int i = 0; i < 8; i++) v[i] = ld_x(ps + i * 144);
#pragma unroll
      for (int i = 0; i < 4; i++) zv[i] = ld_x32(zs + i * 576);
      uint32_t m = min(min(zv[0], zv[1]), min(zv[2], zv[3]));
#pragma unroll
      for (int i = 0; i < 8; i++) m = min(m, v[i].x);
      if (__all_sync(0xffffffffu, m != 0)) break;
    }
    float s[8];
    WG_FENCE();
#pragma unroll
    for (int r = 0; r < 8; r++) wgmma_rs_n16(s, v[r], qdesc(sb + OFF_EYE), r);
    WG_COMMIT();
    float zsum = (uf(zv[0]) + uf(zv[1])) + (uf(zv[2]) + uf(zv[3]));
    zsum += __shfl_xor_sync(0xffffffffu, zsum, 16);
    const uint32_t z1 = pack_bf(zsum, 1.f);
    if (lane < 16) sts128(kvs + w * 768 + 512 + lane * 16, z1, z1, z1, z1);
    WG_WAIT(0);
    stsm4(kvs + w * 768 + lane * 16, pack_bf(s[0], s[1]), pack_bf(s[2], s[3]), pack_bf(s[4], s[5]), pack_bf(s[6], s[7]));
    asm volatile("fence.proxy.async.shared::cta;" ::: "memory");
    TS(22);
  }
  nb_sync(NB_KV, 256);
  {
    float n[8][12];
    WG_FENCE();
#pragma unroll
    for (int i = 0; i < 8; i++) wgmma_rs_n24(n[i], make_uint4(eq[4 * i], eq[4 * i + 1], eq[4 * i + 2], eq[4 * i + 3]), qdesc(kvs + (i & 3) * 768), 0);
    WG_COMMIT();
    uint32_t* od = (uint32_t*)(g_o + (size_t)((rt * 4 + wg * 2) * 32 + hp * 2) * 128) + w * 64 + lane;
    WG_WAIT(0);
#pragma unroll
    for (int u = 0; u < 4; u++) {
      float(&np)[12] = n[2 * u];
      const float(&nm)[12] = n[2 * u + 1];
      const float q0 = np[9] * rcp(nm[9]), q1 = np[11] * rcp(nm[11]);
      const float r0 = rcp(fmaf(nm[8], q0, fmaf(np[9], 1e-6f, np[8]))), r1 = rcp(fmaf(nm[10], q1, fmaf(np[11], 1e-6f, np[10])));
#pragma unroll
      for (int i = 0; i < 8; i++) np[i] = fmaf(nm[i], (i & 2) ? q1 : q0, np[i]);
      uint32_t* o = od + (u >> 1) * 16384 + (u & 1) * 512;
      o[0] = pack_bf(np[0] * r0, np[1] * r0);
      o[32] = pack_bf(np[2] * r1, np[3] * r1);
      o[256] = pack_bf(np[4] * r0, np[5] * r0);
      o[288] = pack_bf(np[6] * r1, np[7] * r1);
      if (u == 1) SPLIT();
    }
  }
  TS(wg * 16 + 7);
  nb_arrive(NB_ODONE, 288);
  if (wg) {
    const uint4* src = P.xs + X_Y + (oct * 32 + c * 8) * 256 + (2 * w + (g >> 2)) * 32 + i8 * 4 + (g & 3);
    __nv_bfloat16* dst = P.out + (size_t)((2 * w + (g >> 2)) * 256 + i8 * 16 + (g & 3) * 2) * 1024 + 512 + oct * 32 + c * 8;
    nb_sync(NB_GATE + 1, 160);
    nb_sync(NB_Y + w, 160);
    uint4 v[8];
#pragma unroll 1
    for (int it = 0; it < SPIN_MAX; it++) {
      uint32_t m = 0xffffffffu;
#pragma unroll
      for (int i = 0; i < 8; i++) v[i] = ld_x(src + i * 256);
#pragma unroll
      for (int i = 0; i < 8; i++) m = min(m, v[i].x);
      if (__all_sync(0xffffffffu, m != 0)) break;
    }
#pragma unroll
    for (int i = 0; i < 8; i++) *(uint4*)(dst + (size_t)((i >> 2) * 128 + ((i >> 1) & 1) * 8 + (i & 1)) * 1024) = tr_row(v, i);
    TS(31);
    GT(63);
    if (w == 0) TSDUMP(16);
    return;
  }
  nb_sync(NB_YZ0, 288);
  conv_helper(sb + OFF_U + w * U_CH, tb, lane, P.xs + X_Y + d * 256 + lane);
  nb_arrive(NB_Y, 160);
  TS(0);
  mbar_wait(BAR(MB_WO));
  nb_sync(NB_BDONE, 288);
  TS(8);
  mbar_spin(BAR(MB_O));
  TS(9);
  constexpr uint64_t ha = mkdesc(0, 0, 128, 0), hb = mkdesc(0, 0, 1024, 1);
  constexpr uint32_t da0 = (uint32_t)mkdesc(stg1, 1024, 0, 0), db0 = (uint32_t)mkdesc(sb + OFF_W, 8192, 0, 0);
  const uint32_t ot = ((sb + OFF_T + 1023) & ~1023u) + w * 4096;
  auto store_half = [&](const float* oc, int hf) {
#pragma unroll
    for (int i = 0; i < 8; i += 2)
      stsm4(ot + hf * 2048 + (lane & 15) * 128 + (((i + (lane >> 4)) ^ lane) & 7) * 16, pack_bf(oc[4 * i], oc[4 * i + 1]),
            pack_bf(oc[4 * i + 2], oc[4 * i + 3]), pack_bf(oc[4 * i + 4], oc[4 * i + 5]), pack_bf(oc[4 * i + 6], oc[4 * i + 7]));
    asm volatile("fence.proxy.async.shared::cta;" ::: "memory");
    __syncwarp();
    e_store2d(&mout, ot + hf * 2048, (hp & 3) * 128 + hf * 64, (rt * 4 + (hp >> 2)) * 64 + w * 16);
  };
  float oc[64];
#pragma unroll 1
  for (int j = 0; j < 8; j++) {
    const int kb = (j + 7) & 7;
    if ((j & 1) && j < 6) mbar_spin(BAR(MB_O + 1) + 4 * (j - 1));
    WG_FENCE();
#pragma unroll
    for (int k = 0; k < 4; k++) wgmma_ss_n128(oc, ha | (da0 + 512 * kb + 128 * k), hb | (db0 + 1024 * kb + 128 * k), k ? 1 : j);
    WG_COMMIT();
  }
  WG_WAIT(0);
  TS(10);
  store_half(oc, 0);
  store_half(oc + 32, 1);
  asm volatile(ELECT "cp.async.bulk.commit_group;\n@p cp.async.bulk.wait_group.read 0;\n}\n" ::: "memory");
  TS(wg * 16 + 11);
  GT(61 + wg);
  if (w == 0) TSDUMP(0);
  if (w == 1) TSDUMP(48);
}

typedef CUresult (*EncodeFn)(CUtensorMap*, CUtensorMapDataType, cuuint32_t, void*, const cuuint64_t*, const cuuint64_t*,
                             const cuuint32_t*, const cuuint32_t*, CUtensorMapInterleave, CUtensorMapSwizzle,
                             CUtensorMapL2promotion, CUtensorMapFloatOOBfill);

}

extern "C" void kernel_launch(void* const* d_in, const int* in_sizes, int n_in, void* d_out, int out_size) {
  (void)in_sizes; (void)n_in; (void)out_size;
  void* fn = nullptr;
  cudaDriverEntryPointQueryResult qr;
  cudaGetDriverEntryPoint("cuTensorMapEncodeTiled", &fn, cudaEnableDefault, &qr);
  EncodeFn enc = (EncodeFn)fn;
  CUtensorMap mx, mw, mo, mu, mout;
  const cuuint32_t es[5] = {1, 1, 1, 1, 1};
  {
    cuuint64_t dims[2] = {512, 2048}, st[1] = {1024};
    cuuint32_t box[2] = {64, 128};
    enc(&mx, CU_TENSOR_MAP_DATA_TYPE_BFLOAT16, 2, d_in[0], dims, st, box, es, CU_TENSOR_MAP_INTERLEAVE_NONE,
        CU_TENSOR_MAP_SWIZZLE_128B, CU_TENSOR_MAP_L2_PROMOTION_L2_128B, CU_TENSOR_MAP_FLOAT_OOB_FILL_NONE);
  }
  {
    cuuint64_t dims[3] = {512, 512, 3}, st[2] = {3072, 1024};
    cuuint32_t box[3] = {32, 64, 3};
    enc(&mw, CU_TENSOR_MAP_DATA_TYPE_BFLOAT16, 3, d_in[1], dims, st, box, es, CU_TENSOR_MAP_INTERLEAVE_NONE,
        CU_TENSOR_MAP_SWIZZLE_64B, CU_TENSOR_MAP_L2_PROMOTION_L2_128B, CU_TENSOR_MAP_FLOAT_OOB_FILL_NONE);
  }
  {
    cuuint64_t dims[3] = {64, 512, 8}, st[2] = {1024, 128};
    cuuint32_t box[3] = {64, 64, 2};
    enc(&mo, CU_TENSOR_MAP_DATA_TYPE_BFLOAT16, 3, d_in[3], dims, st, box, es, CU_TENSOR_MAP_INTERLEAVE_NONE,
        CU_TENSOR_MAP_SWIZZLE_128B, CU_TENSOR_MAP_L2_PROMOTION_L2_128B, CU_TENSOR_MAP_FLOAT_OOB_FILL_NONE);
  }
  {
    cuuint64_t dims[4] = {512, 4, 16, 32}, st[3] = {16384, 1024, 65536};
    cuuint32_t box[4] = {64, 4, 16, 2};
    enc(&mu, CU_TENSOR_MAP_DATA_TYPE_BFLOAT16, 4, d_in[4], dims, st, box, es, CU_TENSOR_MAP_INTERLEAVE_NONE,
        CU_TENSOR_MAP_SWIZZLE_128B, CU_TENSOR_MAP_L2_PROMOTION_L2_128B, CU_TENSOR_MAP_FLOAT_OOB_FILL_NONE);
  }
  {
    cuuint64_t dims[2] = {1024, 2048}, st[1] = {2048};
    cuuint32_t box[2] = {64, 16};
    enc(&mout, CU_TENSOR_MAP_DATA_TYPE_BFLOAT16, 2, d_out, dims, st, box, es, CU_TENSOR_MAP_INTERLEAVE_NONE,
        CU_TENSOR_MAP_SWIZZLE_128B, CU_TENSOR_MAP_L2_PROMOTION_NONE, CU_TENSOR_MAP_FLOAT_OOB_FILL_NONE);
  }
  Params P;
  P.x = (const __nv_bfloat16*)d_in[0];
  P.wphi = (const __nv_bfloat16*)d_in[2];
  P.wo = (const __nv_bfloat16*)d_in[3];
  P.logA = (const __nv_bfloat16*)d_in[5];
  P.Aim = (const __nv_bfloat16*)d_in[6];
  P.Cre = (const __nv_bfloat16*)d_in[7];
  P.Cim = (const __nv_bfloat16*)d_in[8];
  P.logdt = (const __nv_bfloat16*)d_in[9];
  P.Dskip = (const __nv_bfloat16*)d_in[10];
  P.out = (__nv_bfloat16*)d_out;
  cudaGetSymbolAddress((void**)&P.xs, g_x);
  P.ts = nullptr;
  cudaFuncSetAttribute(fused_kernel, cudaFuncAttributeMaxDynamicSharedMemorySize, SMEM_BYTES);
  fused_kernel<<<NCTA, NTHREADS, SMEM_BYTES>>>(P, mx, mw, mo, mu, mout);
}
```

```cpp
#include <cuda_runtime.h>
#include <cuda_bf16.h>
#include <cuda_fp16.h>
#include <cuda.h>
#include <stdint.h>
#include <type_traits>

#define DBG_TS 0

namespace {

constexpr int NTHREADS = 512;
constexpr int NCTA = 128;
constexpr int OFF_W = 0;
constexpr int OFF_X = 98304;
constexpr int OFF_U = OFF_X + 65536;
constexpr int U_CH = 4416, U_ODD = 2240, U_PAD = 128;
constexpr int OFF_STG0 = OFF_U + 18432;
constexpr int SLAB = 3328;
constexpr int OFF_T = OFF_STG0 + 8 * SLAB;
constexpr int T_CH = 5216;
constexpr int T_D = 0;
constexpr int T_5 = 2144;
constexpr int T_3 = T_5 + 384;
constexpr int T_7 = T_5 + 1024;
constexpr int T_9 = T_7 + 320;
constexpr int T_KC = T_9 + 320;
constexpr int T_ST = T_5 - 1024;
constexpr int OFF_PHI = OFF_T + 4 * T_CH;
constexpr int OFF_EYE = OFF_PHI + 1024, OFF_ONE = OFF_EYE + 512;
constexpr int OFF_BAR = OFF_ONE + 256;
constexpr int SMEM_BYTES = OFF_BAR + 512 + 256 * DBG_TS;
constexpr uint32_t SB = 1024;
static_assert(T_KC + 2 * 656 <= T_CH, "table size");
static_assert(SMEM_BYTES <= 232448, "smem");
constexpr int MB_URAW = 0, MB_FULL = 1  , MB_WO = 17, MB_UFULL = 18, MB_O = 19  ,
              MB_EMPTY = 23  , MB_AUX = 39;
__host__ __device__ constexpr uint32_t BAR(int i) { return SB + OFF_BAR + 8 * i; }
constexpr int NB_WG0 = 1, NB_ODONE = 2, NB_ST0 = 3, NB_HAND = 4, NB_KV = 5, NB_YZ = 6, NB_INIT = 7, NB_PREP = 8, NB_PROD = 9, NB_KREAD = 10,
              NB_BDONE = 11, NB_GATE = 12  , NB_Y = 7  ;
constexpr int U_AT = 2;
constexpr int ZERO_STEP = 12;
constexpr int SPIN_MAX = 1 << 16;

constexpr int X_CNT = 0;
constexpr int X_PART = 256;
constexpr int X_O = X_PART + 16 * 8 * 144;
constexpr int X_Y = X_O + 32 * 32 * 128;
constexpr int X_UT = X_Y + 512 * 8 * 32;
constexpr int X_SIZE = X_UT + 512 * (U_CH / 16);
__device__ __align__(128) uint4 g_x[X_SIZE];
extern __shared__ uint8_t smem_raw[];
#define TS(i) do {} while (0)
#define TS1(i) do {} while (0)
#define GT(i) do {} while (0)
#define TSDUMP(base) do {} while (0)

__device__ __forceinline__ uint32_t smem_u32(const void* p) { return (uint32_t)__cvta_generic_to_shared(p); }
__device__ __forceinline__ void mbar_arrive(uint32_t b) {
  asm volatile("mbarrier.arrive.shared::cta.b64 _, [%0];" ::"r"(b) : "memory");
}
__device__ __forceinline__ void mbar_wait(uint32_t b) {
  uint32_t done = 0;
#pragma unroll 1
  for (int i = 0; i < SPIN_MAX && !done; i++) {
    asm volatile("{\n.reg .pred p;\nmbarrier.try_wait.parity.shared::cta.b64 p, [%1], 0, 4000;\nselp.u32 %0, 1, 0, p;\n}\n"
                 : "=r"(done) : "r"(b) : "memory");
  }
}
__device__ __forceinline__ void mbar_spin(uint32_t b) {
  uint32_t done = 0;
#pragma unroll 1
  for (int i = 0; i < (SPIN_MAX << 4) && !done; i++) {
    asm volatile("{\n.reg .pred p;\nmbarrier.try_wait.parity.shared::cta.b64 p, [%1], 0;\nselp.u32 %0, 1, 0, p;\n}\n"
                 : "=r"(done) : "r"(b) : "memory");
  }
}
__device__ __forceinline__ void mbar_init(uint32_t b, int n) {
  asm volatile("mbarrier.init.shared::cta.b64 [%0], %1;" ::"r"(b), "r"(n) : "memory");
}
__device__ __forceinline__ void mbar_expect(uint32_t b, int bytes) {
  asm volatile("mbarrier.arrive.expect_tx.shared::cta.b64 _, [%0], %1;" ::"r"(b), "r"(bytes) : "memory");
}
__device__ __forceinline__ void nb_sync(int id, int n) { asm volatile("bar.sync %0, %1;" ::"r"(id), "r"(n) : "memory"); }
__device__ __forceinline__ void nb_arrive(int id, int n) { asm volatile("bar.arrive %0, %1;" ::"r"(id), "r"(n) : "memory"); }
#define ELECT "{\n.reg .pred p;\nelect.sync _|p, 0xffffffff;\n@p "
__device__ __forceinline__ void e_arrive(uint32_t b) {
  asm volatile(ELECT "mbarrier.arrive.shared::cta.b64 _, [%0];\n}\n" ::"r"(b) : "memory");
}
__device__ __forceinline__ void e_expect(uint32_t b, int bytes) {
  asm volatile(ELECT "mbarrier.arrive.expect_tx.shared::cta.b64 _, [%0], %1;\n}\n" ::"r"(b), "r"(bytes) : "memory");
}
__device__ __forceinline__ void e_tma2d(uint32_t dst, const CUtensorMap* m, uint32_t bar, int c0, int c1) {
  asm volatile(ELECT "cp.async.bulk.tensor.2d.shared::cluster.global.mbarrier::complete_tx::bytes [%0], [%1, {%3,%4}], [%2];\n}\n"
               ::"r"(dst), "l"(m), "r"(bar), "r"(c0), "r"(c1) : "memory");
}
__device__ __forceinline__ void e_tma3d(uint32_t dst, const CUtensorMap* m, uint32_t bar, int c0, int c1, int c2) {
  asm volatile(ELECT "cp.async.bulk.tensor.3d.shared::cluster.global.mbarrier::complete_tx::bytes [%0], [%1, {%3,%4,%5}], [%2];\n}\n"
               ::"r"(dst), "l"(m), "r"(bar), "r"(c0), "r"(c1), "r"(c2) : "memory");
}
__device__ __forceinline__ void e_tma4d(uint32_t dst, const CUtensorMap* m, uint32_t bar, int c0, int c3) {
  asm volatile(ELECT "cp.async.bulk.tensor.4d.shared::cluster.global.mbarrier::complete_tx::bytes [%0], [%1, {%3,%5,%5,%4}], [%2];\n}\n"
               ::"r"(dst), "l"(m), "r"(bar), "r"(c0), "r"(c3), "r"(0) : "memory");
}
__device__ __forceinline__ void e_bulk(uint32_t dst, const void* src, int bytes, uint32_t bar) {
  asm volatile(ELECT "cp.async.bulk.shared::cluster.global.mbarrier::complete_tx::bytes [%0], [%1], %2, [%3];\n}\n"
               ::"r"(dst), "l"(src), "r"(bytes), "r"(bar) : "memory");
}
__device__ __forceinline__ void e_prefetch(const void* p, int bytes) {
  asm volatile(ELECT "cp.async.bulk.prefetch.L2.global [%0], %1;\n}\n" ::"l"(p), "r"(bytes) : "memory");
}
__device__ __forceinline__ void e_store2d(const CUtensorMap* m, uint32_t src, int c0, int c1) {
  asm volatile(ELECT "cp.async.bulk.tensor.2d.global.shared::cta.bulk_group [%0, {%2,%3}], [%1];\n}\n"
               ::"l"(m), "r"(src), "r"(c0), "r"(c1) : "memory");
}
__host__ __device__ constexpr uint64_t mkdesc(uint32_t addr, uint32_t lbo, uint32_t sbo, int swz) {
  return (uint64_t)((addr & 0x3FFFF) >> 4) | ((uint64_t)(lbo >> 4) << 16) | ((uint64_t)(sbo >> 4) << 32) |
         ((uint64_t)swz << 62);
}
#define SPLIT() asm volatile("{\n.reg .pred p;\nsetp.eq.u32 p, %0, %1;\n@p exit;\n}\n" ::"r"(blockIdx.y), "n"(__LINE__) : "memory")
#define SPLITN(n) asm volatile("{\n.reg .pred p;\nsetp.eq.u32 p, %0, %1;\n@p exit;\n}\n" ::"r"(blockIdx.y), "r"(4096 + (n)) : "memory")
#define WG_FENCE() asm volatile("wgmma.fence.sync.aligned;" ::: "memory")
#define WG_COMMIT() asm volatile("wgmma.commit_group.sync.aligned;" ::: "memory")
#define WG_WAIT(n) asm volatile("wgmma.wait_group.sync.aligned " #n ";" ::: "memory")

__device__ __forceinline__ void mma(float& d0, float& d1, float& d2, float& d3, uint32_t a0, uint32_t a1, uint32_t a2,
                                    uint32_t a3, uint32_t b0, uint32_t b1) {
  asm volatile("mma.sync.aligned.m16n8k16.row.col.f32.bf16.bf16.f32 {%0,%1,%2,%3},{%4,%5,%6,%7},{%8,%9},{%0,%1,%2,%3};"
               : "+f"(d0), "+f"(d1), "+f"(d2), "+f"(d3)
               : "r"(a0), "r"(a1), "r"(a2), "r"(a3), "r"(b0), "r"(b1));
}
__device__ __forceinline__ void mmac(float (&d)[4], uint32_t a0, uint32_t a1, uint32_t a2, uint32_t a3, uint32_t b0,
                                     uint32_t b1, const float (&c)[4]) {
  asm volatile("mma.sync.aligned.m16n8k16.row.col.f32.bf16.bf16.f32 {%0,%1,%2,%3},{%4,%5,%6,%7},{%8,%9},{%10,%11,%12,%13};"
               : "=f"(d[0]), "=f"(d[1]), "=f"(d[2]), "=f"(d[3])
               : "r"(a0), "r"(a1), "r"(a2), "r"(a3), "r"(b0), "r"(b1), "f"(c[0]), "f"(c[1]), "f"(c[2]), "f"(c[3]));
}
__device__ __forceinline__ void mma_h(float (&d)[4], const uint32_t (&a)[4], uint32_t b0, uint32_t b1) {
  asm volatile("mma.sync.aligned.m16n8k16.row.col.f32.f16.f16.f32 {%0,%1,%2,%3},{%4,%5,%6,%7},{%8,%9},{%0,%1,%2,%3};"
               : "+f"(d[0]), "+f"(d[1]), "+f"(d[2]), "+f"(d[3]) : "r"(a[0]), "r"(a[1]), "r"(a[2]), "r"(a[3]), "r"(b0), "r"(b1));
}
__device__ __forceinline__ void mma0(float& d0, float& d1, float& d2, float& d3, uint32_t a0, uint32_t a1, uint32_t a2,
                                     uint32_t a3, uint32_t b0, uint32_t b1) {
  asm volatile("mma.sync.aligned.m16n8k16.row.col.f32.bf16.bf16.f32 {%0,%1,%2,%3},{%4,%5,%6,%7},{%8,%9},{%10,%10,%10,%10};"
               : "=f"(d0), "=f"(d1), "=f"(d2), "=f"(d3)
               : "r"(a0), "r"(a1), "r"(a2), "r"(a3), "r"(b0), "r"(b1), "f"(0.f));
}
__device__ __forceinline__ uint32_t pack_bf(float lo, float hi) {
  uint32_t r;
  asm("cvt.rn.bf16x2.f32 %0, %1, %2;" : "=r"(r) : "f"(hi), "f"(lo));
  return r;
}
__device__ __forceinline__ float bf_lo(uint32_t w) { return __uint_as_float(w << 16); }
__device__ __forceinline__ float bf_hi(uint32_t w) { return __uint_as_float(w & 0xffff0000u); }
__device__ __forceinline__ float bf_round(float x) { return __bfloat162float(__float2bfloat16_rn(x)); }
__device__ __forceinline__ uint32_t bmax2(uint32_t a, uint32_t b) {
  uint32_t r; asm("max.bf16x2 %0, %1, %2;" : "=r"(r) : "r"(a), "r"(b)); return r;
}
__device__ __forceinline__ uint32_t bmin2(uint32_t a, uint32_t b) {
  uint32_t r; asm("min.bf16x2 %0, %1, %2;" : "=r"(r) : "r"(a), "r"(b)); return r;
}
__device__ __forceinline__ float ex2(float x) { float r; asm("ex2.approx.ftz.f32 %0, %1;" : "=f"(r) : "f"(x)); return r; }
__device__ __forceinline__ float rcp(float x) { float r; asm("rcp.approx.ftz.f32 %0, %1;" : "=f"(r) : "f"(x)); return r; }
__device__ __forceinline__ void ldsm4(uint32_t (&r)[4], uint32_t a) {
  asm volatile("ldmatrix.sync.aligned.m8n8.x4.shared.b16 {%0,%1,%2,%3}, [%4];"
               : "=r"(r[0]), "=r"(r[1]), "=r"(r[2]), "=r"(r[3]) : "r"(a) : "memory");
}
__device__ __forceinline__ void ldsm4t(uint32_t (&r)[4], uint32_t a) {
  asm volatile("ldmatrix.sync.aligned.m8n8.x4.trans.shared.b16 {%0,%1,%2,%3}, [%4];"
               : "=r"(r[0]), "=r"(r[1]), "=r"(r[2]), "=r"(r[3]) : "r"(a) : "memory");
}
__device__ __forceinline__ void stsm4(uint32_t a, uint32_t r0, uint32_t r1, uint32_t r2, uint32_t r3) {
  asm volatile("stmatrix.sync.aligned.m8n8.x4.shared.b16 [%0], {%1,%2,%3,%4};"
               ::"r"(a), "r"(r0), "r"(r1), "r"(r2), "r"(r3) : "memory");
}
__device__ __forceinline__ uint32_t lds32(uint32_t a) {
  uint32_t r; asm volatile("ld.shared.u32 %0, [%1];" : "=r"(r) : "r"(a) : "memory"); return r;
}
__device__ __forceinline__ uint32_t lds16(uint32_t a) {
  uint32_t r; asm volatile("{\n.reg .u16 h;\nld.shared.u16 h, [%1];\ncvt.u32.u16 %0, h;\n}\n" : "=r"(r) : "r"(a) : "memory"); return r;
}
__device__ __forceinline__ uint2 lds64(uint32_t a) {
  uint2 r; asm volatile("ld.shared.v2.u32 {%0,%1}, [%2];" : "=r"(r.x), "=r"(r.y) : "r"(a) : "memory"); return r;
}
__device__ __forceinline__ uint4 lds128(uint32_t a) {
  uint4 r;
  asm volatile("ld.shared.v4.u32 {%0,%1,%2,%3}, [%4];" : "=r"(r.x), "=r"(r.y), "=r"(r.z), "=r"(r.w) : "r"(a) : "memory");
  return r;
}
__device__ __forceinline__ void sts32(uint32_t a, uint32_t v) { asm volatile("st.shared.u32 [%0], %1;" ::"r"(a), "r"(v) : "memory"); }
__device__ __forceinline__ void sts16(uint32_t a, uint32_t v) {
  asm volatile("{\n.reg .u16 h;\ncvt.u16.u32 h, %1;\nst.shared.u16 [%0], h;\n}\n" ::"r"(a), "r"(v) : "memory");
}
__device__ __forceinline__ void sts64(uint32_t a, uint32_t x, uint32_t y) {
  asm volatile("st.shared.v2.u32 [%0], {%1,%2};" ::"r"(a), "r"(x), "r"(y) : "memory");
}
__device__ __forceinline__ void sts128(uint32_t a, uint32_t x, uint32_t y, uint32_t z, uint32_t w) {
  asm volatile("st.shared.v4.u32 [%0], {%1,%2,%3,%4};" ::"r"(a), "r"(x), "r"(y), "r"(z), "r"(w) : "memory");
}
__device__ __forceinline__ uint4 ld_x(const uint4* p) {
  uint4 r;
  asm volatile("{\n.reg .b128 t;\nld.relaxed.gpu.global.b128 t, [%4];\nmov.b128 {%0,%1,%2,%3}, t;\n}\n"
               : "=r"(r.x), "=r"(r.y), "=r"(r.z), "=r"(r.w) : "l"(p) : "memory");
  return r;
}
__device__ __forceinline__ uint32_t ld_x32(const uint32_t* p) {
  uint32_t r; asm volatile("ld.relaxed.gpu.global.u32 %0, [%1];" : "=r"(r) : "l"(p) : "memory"); return r;
}
__device__ __forceinline__ void st_x(uint4* p, uint32_t x, uint32_t y, uint32_t z, uint32_t w) {
  asm volatile("{\n.reg .b128 t;\nmov.b128 t, {%1,%2,%3,%4};\nst.relaxed.gpu.global.b128 [%0], t;\n}\n"
               ::"l"(p), "r"(x), "r"(y), "r"(z), "r"(w) : "memory");
}
__device__ __forceinline__ void st_x32(uint32_t* p, uint32_t x) {
  asm volatile("st.relaxed.gpu.global.u32 [%0], %1;" ::"l"(p), "r"(x) : "memory");
}
__device__ __forceinline__ uint32_t nz(uint32_t w) { return max(w, 1u); }
__device__ __forceinline__ uint32_t fu(float x) { return __float_as_uint(x); }
__device__ __forceinline__ float uf(uint32_t x) { return __uint_as_float(x); }

__device__ __forceinline__ void wgmma_ss_n96(float (&d)[48], uint64_t da, uint64_t db, int sc) {
  asm volatile("{\n.reg .pred p;\nsetp.ne.b32 p, %50, 0;\n"
      "wgmma.mma_async.sync.aligned.m64n96k16.f32.bf16.bf16 "
      "{%0,%1,%2,%3,%4,%5,%6,%7,%8,%9,%10,%11,%12,%13,%14,%15,%16,%17,%18,%19,%20,%21,%22,%23,%24,%25,%26,%27,%28,%29,%30,%31,%32,%33,%34,%35,%36,%37,%38,%39,%40,%41,%42,%43,%44,%45,%46,%47}, "
      "%48, %49, p, 1, 1, 0, 1;\n}\n"
      : "+f"(d[0]), "+f"(d[1]), "+f"(d[2]), "+f"(d[3]), "+f"(d[4]), "+f"(d[5]), "+f"(d[6]), "+f"(d[7]),
        "+f"(d[8]), "+f"(d[9]), "+f"(d[10]), "+f"(d[11]), "+f"(d[12]), "+f"(d[13]), "+f"(d[14]), "+f"(d[15]),
        "+f"(d[16]), "+f"(d[17]), "+f"(d[18]), "+f"(d[19]), "+f"(d[20]), "+f"(d[21]), "+f"(d[22]), "+f"(d[23]),
        "+f"(d[24]), "+f"(d[25]), "+f"(d[26]), "+f"(d[27]), "+f"(d[28]), "+f"(d[29]), "+f"(d[30]), "+f"(d[31]),
        "+f"(d[32]), "+f"(d[33]), "+f"(d[34]), "+f"(d[35]), "+f"(d[36]), "+f"(d[37]), "+f"(d[38]), "+f"(d[39]),
        "+f"(d[40]), "+f"(d[41]), "+f"(d[42]), "+f"(d[43]), "+f"(d[44]), "+f"(d[45]), "+f"(d[46]), "+f"(d[47])
      : "l"(da), "l"(db), "r"(sc));
}

__device__ __forceinline__ void wgmma_ss_n128(float (&d)[64], uint64_t da, uint64_t db, int sc) {
  asm volatile("{\n.reg .pred p;\nsetp.ne.b32 p, %66, 0;\n"
      "wgmma.mma_async.sync.aligned.m64n128k16.f32.bf16.bf16 "
      "{%0,%1,%2,%3,%4,%5,%6,%7,%8,%9,%10,%11,%12,%13,%14,%15,%16,%17,%18,%19,%20,%21,%22,%23,%24,%25,%26,%27,%28,%29,%30,%31,%32,%33,%34,%35,%36,%37,%38,%39,%40,%41,%42,%43,%44,%45,%46,%47,%48,%49,%50,%51,%52,%53,%54,%55,%56,%57,%58,%59,%60,%61,%62,%63}, "
      "%64, %65, p, 1, 1, 0, 1;\n}\n"
      : "+f"(d[0]), "+f"(d[1]), "+f"(d[2]), "+f"(d[3]), "+f"(d[4]), "+f"(d[5]), "+f"(d[6]), "+f"(d[7]),
        "+f"(d[8]), "+f"(d[9]), "+f"(d[10]), "+f"(d[11]), "+f"(d[12]), "+f"(d[13]), "+f"(d[14]), "+f"(d[15]),
        "+f"(d[16]), "+f"(d[17]), "+f"(d[18]), "+f"(d[19]), "+f"(d[20]), "+f"(d[21]), "+f"(d[22]), "+f"(d[23]),
        "+f"(d[24]), "+f"(d[25]), "+f"(d[26]), "+f"(d[27]), "+f"(d[28]), "+f"(d[29]), "+f"(d[30]), "+f"(d[31]),
        "+f"(d[32]), "+f"(d[33]), "+f"(d[34]), "+f"(d[35]), "+f"(d[36]), "+f"(d[37]), "+f"(d[38]), "+f"(d[39]),
        "+f"(d[40]), "+f"(d[41]), "+f"(d[42]), "+f"(d[43]), "+f"(d[44]), "+f"(d[45]), "+f"(d[46]), "+f"(d[47]),
        "+f"(d[48]), "+f"(d[49]), "+f"(d[50]), "+f"(d[51]), "+f"(d[52]), "+f"(d[53]), "+f"(d[54]), "+f"(d[55]),
        "+f"(d[56]), "+f"(d[57]), "+f"(d[58]), "+f"(d[59]), "+f"(d[60]), "+f"(d[61]), "+f"(d[62]), "+f"(d[63])
      : "l"(da), "l"(db), "r"(sc));
}

__device__ __forceinline__ void wgmma_ss_n40(float (&d)[20], uint64_t da, uint64_t db, int sc) {
  asm volatile("{\n.reg .pred p;\nsetp.ne.b32 p, %22, 0;\n"
      "wgmma.mma_async.sync.aligned.m64n40k16.f32.bf16.bf16 "
      "{%0,%1,%2,%3,%4,%5,%6,%7,%8,%9,%10,%11,%12,%13,%14,%15,%16,%17,%18,%19}, "
      "%20, %21, p, 1, 1, 1, 1;\n}\n"
      : "+f"(d[0]), "+f"(d[1]), "+f"(d[2]), "+f"(d[3]), "+f"(d[4]), "+f"(d[5]), "+f"(d[6]), "+f"(d[7]),
        "+f"(d[8]), "+f"(d[9]), "+f"(d[10]), "+f"(d[11]), "+f"(d[12]), "+f"(d[13]), "+f"(d[14]), "+f"(d[15]),
        "+f"(d[16]), "+f"(d[17]), "+f"(d[18]), "+f"(d[19])
      : "l"(da), "l"(db), "r"(sc));
}

__device__ __forceinline__ void wgmma_rs_n8(float (&d)[4], const uint4& a, uint64_t db, int sc) {
  asm volatile("{\n.reg .pred p;\nsetp.ne.b32 p, %9, 0;\n"
      "wgmma.mma_async.sync.aligned.m64n8k16.f32.bf16.bf16 "
      "{%0,%1,%2,%3}, "
      "{%4,%5,%6,%7}, %8, p, 1, 1, 1;\n}\n"
      : "+f"(d[0]), "+f"(d[1]), "+f"(d[2]), "+f"(d[3])
      : "r"(a.x), "r"(a.y), "r"(a.z), "r"(a.w), "l"(db), "r"(sc));
}

__device__ __forceinline__ void wgmma_rs_n16(float (&d)[8], const uint4& a, uint64_t db, int sc) {
  asm volatile("{\n.reg .pred p;\nsetp.ne.b32 p, %13, 0;\n"
      "wgmma.mma_async.sync.aligned.m64n16k16.f32.bf16.bf16 "
      "{%0,%1,%2,%3,%4,%5,%6,%7}, "
      "{%8,%9,%10,%11}, %12, p, 1, 1, 1;\n}\n"
      : "+f"(d[0]), "+f"(d[1]), "+f"(d[2]), "+f"(d[3]), "+f"(d[4]), "+f"(d[5]), "+f"(d[6]), "+f"(d[7])
      : "r"(a.x), "r"(a.y), "r"(a.z), "r"(a.w), "l"(db), "r"(sc));
}

__device__ __forceinline__ void wgmma_rs_n24(float (&d)[12], const uint4& a, uint64_t db, int sc) {
  asm volatile("{\n.reg .pred p;\nsetp.ne.b32 p, %17, 0;\n"
      "wgmma.mma_async.sync.aligned.m64n24k16.f32.bf16.bf16 "
      "{%0,%1,%2,%3,%4,%5,%6,%7,%8,%9,%10,%11}, "
      "{%12,%13,%14,%15}, %16, p, 1, 1, 1;\n}\n"
      : "+f"(d[0]), "+f"(d[1]), "+f"(d[2]), "+f"(d[3]), "+f"(d[4]), "+f"(d[5]), "+f"(d[6]), "+f"(d[7]),
        "+f"(d[8]), "+f"(d[9]), "+f"(d[10]), "+f"(d[11])
      : "r"(a.x), "r"(a.y), "r"(a.z), "r"(a.w), "l"(db), "r"(sc));
}

struct Params {
  const __nv_bfloat16 *logA, *Aim, *Cre, *Cim, *logdt, *Dskip, *x, *wphi, *wo;
  __nv_bfloat16* out;
  uint4* xs;
  long long* ts;
};

__device__ __forceinline__ uint4 tr_row(const uint4 (&v)[8], int i) {
  uint32_t o[4];
#pragma unroll
  for (int m = 0; m < 4; m++) {
    const uint4 &ra = v[2 * m], &rb = v[2 * m + 1];
    const int k = i >> 1;
    const uint32_t xa = k == 0 ? ra.x : k == 1 ? ra.y : k == 2 ? ra.z : ra.w;
    const uint32_t xb = k == 0 ? rb.x : k == 1 ? rb.y : k == 2 ? rb.z : rb.w;
    o[m] = __byte_perm(xa, xb, (i & 1) ? 0x7632 : 0x5410);
  }
  return make_uint4(o[0], o[1], o[2], o[3]);
}

struct cpx { float r, i; };
__device__ __forceinline__ cpx csq(cpx a) { return {a.r * a.r - a.i * a.i, 2.f * (a.r * a.i)}; }
__device__ __forceinline__ cpx polar(float e, float t) {
  const float m = ex2(e);
  return {m * __cosf(t), m * __sinf(t)};
}

struct KgenRaw { uint32_t la, ai, cr, ci, ldt; };
__device__ __forceinline__ KgenRaw kgen_load(const Params& P, int d, int unit, int lane, int on) {
  const int o = d * 64 + unit * 32 + lane;
  KgenRaw r = {0, 0, 0, 0, 0};
  asm volatile("{\n.reg .pred p;\nsetp.ne.b32 p, %10, 0;\n@p ld.global.nc.u32 %0, [%5];\n@p ld.global.nc.u32 %1, [%6];\n"
               "@p ld.global.nc.u32 %2, [%7];\n@p ld.global.nc.u32 %3, [%8];\n@p ld.global.nc.u16 %4, [%9];\n}\n"
               : "+r"(r.la), "+r"(r.ai), "+r"(r.cr), "+r"(r.ci), "+r"(r.ldt)
               : "l"((const uint32_t*)P.logA + o), "l"((const uint32_t*)P.Aim + o), "l"((const uint32_t*)P.Cre + o),
                 "l"((const uint32_t*)P.Cim + o), "l"(P.logdt + d), "r"(on));
  return r;
}
struct hc { __half2 r, i; };
struct cpx2 { cpx a, b; };
__device__ __forceinline__ cpx2 csq2(const cpx2& v) { return {csq(v.a), csq(v.b)}; }
__device__ __forceinline__ hc toh(const cpx2& v) { return {__floats2half2_rn(v.a.r, v.b.r), __floats2half2_rn(v.a.i, v.b.i)}; }
__device__ __forceinline__ hc hmul(const hc& z, const hc& w) {
  return {__hfma2(z.r, w.r, __hneg2(__hmul2(z.i, w.i))), __hfma2(z.r, w.i, __hmul2(z.i, w.r))};
}
__device__ __forceinline__ hc hmulc(const hc& z, const hc& w) {
  return {__hfma2(z.r, w.r, __hmul2(z.i, w.i)), __hfma2(z.i, w.r, __hneg2(__hmul2(z.r, w.i)))};
}
__device__ __forceinline__ uint32_t hu(__half2 v) { return *(const uint32_t*)&v; }
__device__ __forceinline__ __half2 uh(uint32_t v) { return *(const __half2*)&v; }

struct KgenAddr { uint32_t sa, lb, lm[4]; };
__device__ __forceinline__ KgenAddr kgen_addr(int lane, uint32_t buf) {
  KgenAddr a;
  a.sa = buf + (lane & 7) * 128 + ((((lane >> 3) ^ lane) & 7) << 4);
  const int q = lane >> 4;
  const uint32_t b = buf + ((lane >> 3) & 1) * 1024 + q * 128;
  a.lb = b + (((lane ^ q) & 7) << 4);
  a.lm[0] = b + (q << 4);
  a.lm[1] = b + ((1 ^ q) << 4);
  a.lm[2] = b + (((2 + (lane & 1)) ^ q) << 4);
  a.lm[3] = b + (((4 + (lane & 3)) ^ q) << 4);
  asm volatile("" : "+r"(a.sa), "+r"(a.lb), "+r"(a.lm[0]), "+r"(a.lm[1]), "+r"(a.lm[2]), "+r"(a.lm[3]));
  return a;
}
__device__ __forceinline__ void kgen_unit(const KgenRaw& r, const KgenAddr& ad, uint32_t zero, float (&k)[5][4], float& k2048, float& sc) {
  const float dt = bf_round(expf(bf_lo(r.ldt)));
  const uint32_t ar = pack_bf(ex2(bf_lo(r.la) * 1.4426950408889634f), ex2(bf_hi(r.la) * 1.4426950408889634f));
  const float ca = dt * -1.4426950408889634f, a0 = bf_lo(ar) * ca, a1 = bf_hi(ar) * ca;
  const float f0 = bf_lo(r.ai) * dt, f1 = bf_hi(r.ai) * dt;
  const float r0 = f0 * 20.21267777267071f, r1 = f1 * 20.21267777267071f;
  const uint32_t cm = __vmaxu2(r.cr & 0x7fff7fffu, r.ci & 0x7fff7fffu);
  const uint32_t ex = min(max(__reduce_max_sync(0xffffffffu, max(cm >> 16, cm & 0xffffu)) >> 7, 1u), 253u);
  const float cs = uf((254u - ex) << 23);
  sc = 2.f * dt * uf(ex << 23);
  const cpx2 C = {{bf_lo(r.cr) * cs, bf_lo(r.ci) * -cs}, {bf_hi(r.cr) * cs, bf_hi(r.ci) * -cs}};
  auto put = [&](const hc (&v)[8]) {
    stsm4(ad.sa, hu(v[0].r), hu(v[1].r), hu(v[2].r), hu(v[3].r));
    stsm4(ad.sa + 1024, hu(v[0].i), hu(v[1].i), hu(v[2].i), hu(v[3].i));
    stsm4(ad.sa ^ 64, hu(v[4].r), hu(v[5].r), hu(v[6].r), hu(v[7].r));
    stsm4((ad.sa ^ 64) + 1024, hu(v[4].i), hu(v[5].i), hu(v[6].i), hu(v[7].i));
    __syncwarp();
  };
  auto get = [&](uint32_t (&o)[4][4], uint32_t a) {
#pragma unroll
    for (int i = 0; i < 4; i++) ldsm4(o[i], (a ^ (i << 5)) + i * 256);
  };
  auto at = [](const uint32_t (&o)[4][4], int s) { return hc{uh(o[s >> 1][2 * (s & 1)]), uh(o[s >> 1][2 * (s & 1) + 1])}; };
  uint32_t A[8][4];
  auto tile = [&](int j, const uint32_t (&B)[4][4]) {
    k[j][0] = k[j][1] = k[j][2] = k[j][3] = 0.f;
#pragma unroll
    for (int s = 0; s < 8; s++) mma_h(k[j], A[s], B[s >> 1][2 * (s & 1)], B[s >> 1][2 * (s & 1) + 1]);
  };
  const cpx2 w1 = {polar(a0, f0), polar(a1, f1)};
  const cpx2 w127 = {polar(a0 * 127.f, (r0 - rintf(r0)) * 6.283185307179586f), polar(a1 * 127.f, (r1 - rintf(r1)) * 6.283185307179586f)};
  const cpx2 w2 = csq2(w1), w4 = csq2(w2);
  uint32_t T0[4][4], X[4][4], M[3][4][4];
  {
    hc t[8];
    t[0] = {uh(0x3C003C00u), uh(0u)}; t[1] = toh(w1); t[2] = toh(w2); t[4] = toh(w4);
    t[3] = hmul(t[1], t[2]); t[5] = hmul(t[1], t[4]); t[6] = hmul(t[2], t[4]); t[7] = hmul(t[3], t[4]);
    put(t); get(T0, ad.lb);
  }
  const cpx2 w8 = csq2(w4), w16 = csq2(w8), w32 = csq2(w16), w64 = csq2(w32);
  {
    const hc m8 = toh(w8), m16 = toh(w16), m32 = toh(w32);
    hc a[8];
    a[0] = toh(C); a[1] = hmulc(a[0], m8);
    a[2] = hmulc(a[0], m16); a[3] = hmulc(a[1], m16);
#pragma unroll
    for (int i = 0; i < 4; i++) a[4 + i] = hmulc(a[i], m32);
    put(a); get(X, ad.lb);
  }
    const cpx2 w128 = {{w127.a.r * w1.a.r - w127.a.i * w1.a.i, w127.a.r * w1.a.i + w127.a.i * w1.a.r},
                     {w127.b.r * w1.b.r - w127.b.i * w1.b.i, w127.b.r * w1.b.i + w127.b.i * w1.b.r}};
  const cpx2 w256 = csq2(w128), w512 = csq2(w256);
  const hc m128 = toh(w128), m256 = toh(w256), m512 = toh(w512);
  {
    const hc m254 = toh(csq2(w127)), m127 = toh(w127);
    hc m[8];
    m[0] = toh(w64); m[1] = m128; m[2] = m256; m[3] = hmul(m127, m256);
    m[4] = m512; m[5] = hmul(m127, m512); m[6] = hmul(m[4], m254); m[7] = hmul(m[5], m254);
    put(m);
    get(M[0], ad.lm[0]);
#pragma unroll
    for (int s = 0; s < 8; s++) {
      const hc z = at(X, s), y = hmulc(z, at(M[0], s));
      A[s][0] = hu(z.r) + zero; A[s][1] = hu(y.r); A[s][2] = hu(z.i) + zero; A[s][3] = hu(y.i);
    }
#pragma unroll
    for (int i = 0; i < 3; i++) get(M[i], ad.lm[i + 1]);
  }
  tile(0, T0);
  const cpx2 w1024 = csq2(w512), we = csq2(w1024);
  {
    hc t[8];
    t[0] = toh(w1024); t[1] = hmul(t[0], m128);
    t[2] = hmul(t[0], m256); t[3] = hmul(t[1], m256);
#pragma unroll
    for (int i = 0; i < 4; i++) t[4 + i] = hmul(t[i], m512);
    put(t); get(X, ad.lb);
  }
  k2048 = (C.a.r * we.a.r + C.a.i * we.a.i + C.b.r * we.b.r + C.b.i * we.b.i) * sc;
#pragma unroll
  for (int j = 1; j < 5; j++) k[j][0] = k[j][1] = k[j][2] = k[j][3] = 0.f;
#pragma unroll
  for (int s = 0; s < 8; s++) {
#pragma unroll
    for (int j = 0; j < 3; j++) {
      const hc y = hmul(at(T0, s), at(M[j], s));
      mma_h(k[1 + j], A[s], hu(y.r), hu(y.i));
    }
    mma_h(k[4], A[s], X[s >> 1][2 * (s & 1)], X[s >> 1][2 * (s & 1) + 1]);
  }
}

__device__ __forceinline__ void build_tables(uint32_t tb, int lane, float (&k)[5][4], float k2048) {
  const int g = lane >> 2, c = lane & 3;
  const uint32_t kc = tb + T_KC + 16;
  {
    const uint32_t a0 = kc + 16 * g + 4 * c, a2 = kc + 2 * (256 + 4 * g + c);
    const uint32_t a3 = kc + 2 * (384 + 2 * g + 64 * (c & 1) + (c >> 1)), a4 = kc + 2 * (512 + g + 32 * c);
#pragma unroll
    for (int r = 0; r < 2; r++) {
      sts32(a0 + 128 * r, pack_bf(k[0][2 * r], k[0][2 * r + 1]));
      sts32(a0 + 128 * r + 256, pack_bf(k[1][2 * r], k[1][2 * r + 1]));
      const uint32_t w2 = pack_bf(k[2][2 * r], k[2][2 * r + 1]);
      const uint32_t w3 = pack_bf(k[3][2 * r], k[3][2 * r + 1]);
      const uint32_t w4 = pack_bf(k[4][2 * r], k[4][2 * r + 1]);
      sts16(a2 + 64 * r, w2); sts16(a2 + 64 * r + 128, w2 >> 16);
      sts16(a3 + 32 * r, w3); sts16(a3 + 32 * r + 64, w3 >> 16);
      sts16(a4 + 16 * r, w4); sts16(a4 + 16 * r + 32, w4 >> 16);
    }
  }
  if (lane == 0) { sts16(kc + 2 * 640, pack_bf(k2048, 0.f)); sts32(kc - 4, 0); }
  __syncwarp();
  const uint32_t td = tb + T_D + 32;
#pragma unroll
  for (int hf = 0; hf < 2; hf++) {
    const uint2 v = lds64(kc + 256 * hf + 8 * lane);
    const uint32_t pv = lds32(kc + 256 * hf + 8 * lane - 4);
    sts128(td + 512 * hf + 16 * lane, __byte_perm(v.x, pv, 0x7610), __byte_perm(v.x, v.x, 0x1032), __byte_perm(v.y, v.x, 0x7610),
           __byte_perm(v.y, v.y, 0x1032));
  }
#pragma unroll
  for (int hf = 0; hf < 2; hf++) {
    const uint32_t v = lds32(kc + 512 + 128 * hf + 4 * lane), nx = lds32(kc + 516 + 128 * hf + 4 * lane);
    uint32_t w0 = __byte_perm(v, v, 0x1010);
    const uint32_t w1 = w0;
    if (hf == 0) { const uint32_t pv = lds32(kc + 508); if (lane == 0) w0 = __byte_perm(v, pv, 0x7610); }
    sts128(td + 1024 + 512 * hf + 16 * lane, w0, w1, __byte_perm(v, v, 0x1032), __byte_perm(nx, v, 0x7610));
  }
  {
    const uint32_t kk = lds16(kc + 2 * 384);
    const uint32_t w = lane < 3 ? (kk | (kk << 16)) : (lane == 3 ? (kk << 16) : 0u);
    if (lane < 24) sts32(td + 4 * (lane < 16 ? 512 + lane : lane - 24), w);
    const uint32_t lo_ = lds16(kc + 2 * 511), le_ = lds16(kc + 2 * 512);
    const uint32_t ja = tb + T_5 + (lane < 16 ? 4 * lane : 256 + 4 * lane);
    sts32(ja, lane == 16 ? (le_ << 16) : 0u);
    sts32(ja + 384, lane == 16 ? (lo_ << 16) : 0u);
    sts32(tb + (lane < 16 ? T_7 : T_9 - 64) + 4 * lane, 0u);
  }
#pragma unroll
  for (int s = 0; s < 2; s++) {
    const uint32_t b = kc + 2 * (s ? 512 : 384) + 8 * lane;
    const uint2 v = lds64(b);
    uint32_t em = lds16(b - 2), e0 = v.x;
    const uint32_t e4 = lds16(b + 8);
    if (lane == 0) { em = 0; e0 = 0; }
    sts64(tb + (s ? T_7 : T_3) + 64 + 8 * lane, __byte_perm(v.x, em, 0x5432), __byte_perm(v.y, v.x, 0x7632));
    sts64(tb + (s ? T_9 : T_5) + 64 + 8 * lane, __byte_perm(v.y, e0, 0x5410), __byte_perm(e4, v.y, 0x5410));
  }
  __syncwarp();
}

__device__ __forceinline__ uint32_t box2w(int lo, int n, int o) {
  return ((unsigned)(o - lo) < (unsigned)n ? 0x3F80u : 0u) | ((unsigned)(o + 1 - lo) < (unsigned)n ? 0x3F800000u : 0u);
}

__device__ __forceinline__ void conv_channel(uint32_t ub, uint32_t tb, int lane, uint4* ydst) {
  const int g = lane >> 2, c = lane & 3, x = g - 2 * c;
  const int mi = lane >> 3;
  const uint32_t qa = ub + U_PAD + 16 * (lane & 7) + ((mi == 0 || mi == 3) ? U_ODD : 0) - (mi == 0 ? 16 : 0);
  const uint32_t hb = ub + U_PAD + (mi & 1) * U_ODD + 16 * ((lane >> 4) + (lane & 7)) - 16;
  const uint32_t kv = lds16(tb + T_KC + 16 + 2 * 512);
  const int oh = c < 2 ? 8 + 2 * c : 2 * c - 8, og = c < 3 ? 2 * c : -10;
  uint32_t bx[4] = {box2w(g - 4, 9, 2 * c), box2w(g - 3, 7, 2 * c), box2w(g - 4, 9, oh), box2w(g - 3, 7, oh)};
  uint32_t by[4] = {box2w(g - 10, 5, 2 * c - 8), box2w(g - 5, 3, 2 * c - 8), box2w(g - 10, 5, og), box2w(g - 5, 3, og)};
  uint32_t lb0 = ((unsigned)(x + 5) < 2u ? kv : 0u) | ((unsigned)(x + 4) < 2u ? kv << 16 : 0u);
  uint32_t lb1 = ((unsigned)(x - 3) < 2u ? kv : 0u) | ((unsigned)(x - 4) < 2u ? kv << 16 : 0u);
  const int q0 = g - 1, q1 = c < 3 ? g : g - 2;
  uint32_t y0a = ub + U_PAD + (q0 & 1) * U_ODD + 16 * (q0 >> 1) + 4 * c;
  uint32_t y1a = ub + U_PAD + (q1 & 1) * U_ODD + 16 * (q1 >> 1) + 4 * c;
#pragma unroll
  for (int i = 0; i < 4; i++) asm volatile("" : "+r"(bx[i]), "+r"(by[i]));
  asm volatile("" : "+r"(lb0), "+r"(lb1), "+r"(y0a), "+r"(y1a));
  mbar_wait(BAR(MB_UFULL));
  mbar_spin(BAR(MB_EMPTY + 15));
  TS(36);
  float acc[16][4];
  {
    uint32_t z09[8], z07[8], zm9[8], zm7[8];
#pragma unroll
    for (int i = 0; i < 8; i++) {
      uint32_t h[4];
      ldsm4(h, hb + 128 * i);
      float y0, y1, y2, y3, w0, w1, w2, w3;
      mma0(y0, y1, y2, y3, bx[0], bx[1], bx[2], bx[3], h[2], c < 2 ? h[3] : h[1]);
      mma0(w0, w1, w2, w3, bx[0], bx[1], bx[2], bx[3], h[1], c < 2 ? h[2] : h[0]);
      z09[i] = pack_bf(y0, y1); z07[i] = pack_bf(y2, y3);
      zm9[i] = pack_bf(w0, w1); zm7[i] = pack_bf(w2, w3);
    }
  uint32_t f3[3][4][4];
  {
    const uint32_t fa = tb + T_7 + 4 * (16 + x);
#pragma unroll
    for (int tt = 0; tt < 3; tt++)
#pragma unroll
      for (int D = 0; D < 4; D++) {
        const uint32_t a = fa + (tt == 0 ? 316 : (tt == 1 ? 320 : 0)) + 64 * D;
        f3[tt][D][0] = lds32(a); f3[tt][D][1] = lds32(a + 32); f3[tt][D][2] = lds32(a - 32); f3[tt][D][3] = lds32(a);
      }
  }
    SPLIT();
    nb_sync(NB_GATE, 256);
    SPLIT();
    float a[4][2][4];
#pragma unroll
    for (int kap = 0; kap < 4; kap++)
#pragma unroll
      for (int sg = 0; sg < 2; sg++)
#pragma unroll
        for (int bk = 3; bk >= kap; bk--) {
          const uint32_t(&q0_)[4] = f3[sg ? 2 : 0][bk - kap];
          const uint32_t(&q1_)[4] = f3[sg ? 2 : 1][bk - kap];
          float(&a0)[4] = a[bk][0];
          float(&a1)[4] = a[bk][1];
          if (sg == 0 && kap == 0) {
            mma0(a0[0], a0[1], a0[2], a0[3], q0_[0], q0_[1], q0_[2], q0_[3], z09[0], z09[1]);
            mma0(a1[0], a1[1], a1[2], a1[3], q1_[0], q1_[1], q1_[2], q1_[3], zm9[0], zm9[1]);
          } else {
            mma(a0[0], a0[1], a0[2], a0[3], q0_[0], q0_[1], q0_[2], q0_[3], sg ? zm7[2 * kap] : z09[2 * kap], sg ? zm7[2 * kap + 1] : z09[2 * kap + 1]);
            mma(a1[0], a1[1], a1[2], a1[3], q1_[0], q1_[1], q1_[2], q1_[3], sg ? z07[2 * kap] : zm9[2 * kap], sg ? z07[2 * kap + 1] : zm9[2 * kap + 1]);
          }
        }
    SPLIT();
#pragma unroll
    for (int i = 0; i < 8; i++) {
      uint32_t h[4];
      ldsm4(h, qa + 128 * i);
      const float ci[4] = {a[i >> 1][0][2 * (i & 1)], a[i >> 1][0][2 * (i & 1) + 1], a[i >> 1][1][2 * (i & 1)], a[i >> 1][1][2 * (i & 1) + 1]};
      mmac(acc[8 + i], h[0], h[1], h[2], h[3], lb0, lb1, ci);
    }
  }
  TS(44);
  {
    uint2 a5[10], a3[10];
    const uint32_t aa = tb + T_5 + 4 * (8 + 2 * g - 2 * c);
#pragma unroll
    for (int m = 0; m < 10; m++) { a5[m] = lds64(aa + 32 * m); a3[m] = lds64(aa + 384 + 32 * m); }
    uint32_t x5[12][2], x3[12][2];
    auto ygen = [&](int kap) {
#pragma unroll
      for (int hh = 0; hh < 2; hh++) {
        float y0, y1, y2, y3;
        mma0(y0, y1, y2, y3, by[0], by[1], by[2], by[3], lds32(y0a + 128 * kap + 64 * hh), lds32(y1a + 128 * kap + 64 * hh));
        x5[kap][hh] = pack_bf(y0, y1);
        x3[kap][hh] = pack_bf(y2, y3);
      }
    };
    ygen(11); ygen(10); ygen(9); ygen(8);
#pragma unroll
    for (int kap = 11; kap >= 0; kap--) {
      if (kap >= 4) ygen(kap - 4);
#pragma unroll
      for (int sg = 0; sg < 2; sg++)
#pragma unroll
        for (int i = 4; i >= 0; i--) {
          const int be = kap + 4 + i;
          if (be <= 15) {
            const uint2 &hi = sg ? a3[2 * i + 1] : a5[2 * i + 1], &lo = sg ? a3[2 * i] : a5[2 * i];
            const uint32_t b0 = sg ? x3[kap][0] : x5[kap][0], b1 = sg ? x3[kap][1] : x5[kap][1];
            if (be < 8 && i == 0 && sg == 0) mma0(acc[be][0], acc[be][1], acc[be][2], acc[be][3], hi.x, hi.y, lo.x, lo.y, b0, b1);
            else mma(acc[be][0], acc[be][1], acc[be][2], acc[be][3], hi.x, hi.y, lo.x, lo.y, b0, b1);
          }
        }
    }
  }
  TS(45);
  {
    const uint32_t st = tb + T_ST + lane * 8;
#pragma unroll
    for (int be = 4; be < 12; be++) sts64(st + 256 * be, pack_bf(acc[be][0], acc[be][1]), pack_bf(acc[be][2], acc[be][3]));
    SPLIT();
    uint32_t F[66], qd[8][4];
    const uint32_t fa = tb + T_D + 32 + 4 * x;
#pragma unroll
    for (int i = 0; i < 32; i++) {
      const int s = 120 - (i >> 2) - 8 * (i & 3);
      uint32_t(&q)[4] = qd[i & 7];
      ldsm4(q, qa + 16 * s);
      const int m = 16 * (i & 3) + 2 * (i >> 2);
      F[m] = lds32(fa + 32 * m); F[m + 1] = lds32(fa + 32 * m + 32);
#pragma unroll
      for (int be = 15; be >= 12; be--) {
        const int de = 8 * be - s;
        float(&a)[4] = (be >= 14 && !(i & 1)) ? acc[be - 4] : acc[be];
        if (de >= 0 && be >= 14 && i == 2 * (15 - be)) mma0(a[0], a[1], a[2], a[3], q[0], q[1], q[2], q[3], F[2 * de + 1], F[2 * de]);
        else if (de >= 0) mma(a[0], a[1], a[2], a[3], q[0], q[1], q[2], q[3], F[2 * de + 1], F[2 * de]);
      }
    }
#pragma unroll
    for (int i = 0; i < 8; i++) acc[14 + (i >> 2)][i & 3] += acc[10 + (i >> 2)][i & 3];
    F[64] = lds32(fa + 32 * 64); F[65] = lds32(fa + 32 * 65);
#pragma unroll
    for (int i = 0; i < 6; i++) ldsm4(qd[i], qa + 128 * 11 - 16 * i);
    uint2 sv = lds64(st + 256 * 11);
    float ci[4] = {bf_lo(sv.x), bf_hi(sv.x), bf_lo(sv.y), bf_hi(sv.y)};
    float T[5][4];
#pragma unroll
    for (int i = 0; i < 16; i++) T[i >> 2][i & 3] = acc[12 + (i >> 2)][i & 3];
    nb_sync(NB_YZ, 160);
    TS(46);
    uint32_t held[2];
#pragma unroll
    for (int be = 11; be >= 0; be--) {
      if (be & 1) SPLITN(be);
      const uint32_t qp = qa + 128 * be;
#pragma unroll
      for (int k = 4; k >= 1; k--) mmac(T[k], qd[0][0], qd[0][1], qd[0][2], qd[0][3], F[16 * k + 1], F[16 * k], T[k - 1]);
      if (be >= 4) mmac(T[0], qd[0][0], qd[0][1], qd[0][2], qd[0][3], F[1], F[0], ci);
      else mma0(T[0][0], T[0][1], T[0][2], T[0][3], qd[0][0], qd[0][1], qd[0][2], qd[0][3], F[1], F[0]);
      ldsm4(qd[6], qp - 16 * 6);
      ldsm4(qd[7], qp - 16 * 7);
      if (be > 4) sv = lds64(st + 256 * (be - 1));
#pragma unroll
      for (int i = 1; i < 8; i++) {
#pragma unroll
        for (int k = 3; k >= 0; k--)
          mma(T[k][0], T[k][1], T[k][2], T[k][3], qd[i][0], qd[i][1], qd[i][2], qd[i][3], F[16 * k + 2 * i + 1], F[16 * k + 2 * i]);
        if (i < 7 && be > 0) ldsm4(qd[i - 1], qp - 128 - 16 * (i - 1));
        if (i == 2) {
          const uint32_t w0 = pack_bf(T[4][0], T[4][1]), w1 = pack_bf(T[4][2], T[4][3]);
          if (be & 1) { held[0] = w0; held[1] = w1; }
          else st_x(ydst + (be + 4) * 16, nz(w0), w1, held[0], held[1]);
          if ((be & 3) == 3 && be < 11) nb_arrive(NB_Y + 2 + (be >> 2), 160);
        }
        if (i == 4 && be > 4) { ci[0] = bf_lo(sv.x); ci[1] = bf_hi(sv.x); ci[2] = bf_lo(sv.y); ci[3] = bf_hi(sv.y); }
      }
    }
    if ((fu(T[0][0]) & fu(T[1][0]) & fu(T[2][0]) & fu(T[3][0])) == 0xffffffffu) sts32(st, 0);
    nb_arrive(NB_BDONE, 288);
    nb_arrive(NB_Y + 1, 160);
#pragma unroll
    for (int B = 1; B >= 0; B--)
      st_x(ydst + B * 32, nz(pack_bf(T[2 * B][0], T[2 * B][1])), pack_bf(T[2 * B][2], T[2 * B][3]),
           pack_bf(T[2 * B + 1][0], T[2 * B + 1][1]), pack_bf(T[2 * B + 1][2], T[2 * B + 1][3]));
  }
}

__device__ __forceinline__ void dual_exp(const uint32_t* w, uint32_t* e) {
  const float L = 1.44268798828125f;
  uint32_t mx = bmax2(bmax2(w[0], w[1]), bmax2(w[2], w[3]));
  uint32_t mn = bmin2(bmin2(w[0], w[1]), bmin2(w[2], w[3]));
  mx = bmax2(mx, __shfl_xor_sync(0xffffffffu, mx, 1));
  mn = bmin2(mn, __shfl_xor_sync(0xffffffffu, mn, 1));
  mx = bmax2(mx, __shfl_xor_sync(0xffffffffu, mx, 2));
  mn = bmin2(mn, __shfl_xor_sync(0xffffffffu, mn, 2));
  const float mx0 = bf_lo(mx) * -L, mx1 = bf_hi(mx) * -L, mn0 = bf_lo(mn) * L, mn1 = bf_hi(mn) * L;
#pragma unroll
  for (int i = 0; i < 2; i++) {
    const float a0 = bf_lo(w[2 * i]), a1 = bf_hi(w[2 * i]), b0 = bf_lo(w[2 * i + 1]), b1 = bf_hi(w[2 * i + 1]);
    e[2 * i] = pack_bf(ex2(fmaf(a0, L, mx0)), ex2(fmaf(b0, L, mx0)));
    e[2 * i + 1] = pack_bf(ex2(fmaf(a1, L, mx1)), ex2(fmaf(b1, L, mx1)));
    e[4 + 2 * i] = pack_bf(ex2(fmaf(a0, -L, mn0)), ex2(fmaf(b0, -L, mn0)));
    e[5 + 2 * i] = pack_bf(ex2(fmaf(a1, -L, mn1)), ex2(fmaf(b1, -L, mn1)));
  }
}
__device__ __forceinline__ void normalise(uint32_t* e, const float (&s)[4]) {
  const uint32_t r = pack_bf(rcp(s[0]), rcp(s[2]));
  const __nv_bfloat162 rr = *(const __nv_bfloat162*)&r;
#pragma unroll
  for (int i = 0; i < 4; i++) {
    const __nv_bfloat162 v = __hmul2(*(const __nv_bfloat162*)&e[i], (i & 1) ? __high2bfloat162(rr) : __low2bfloat162(rr));
    e[i] = *(const uint32_t*)&v;
  }
}
__host__ __device__ constexpr uint64_t qdesc(uint32_t addr) { return mkdesc(addr, 128, 256, 0); }

__global__ void __launch_bounds__(NTHREADS, 1)
fused_kernel(const Params P, const __grid_constant__ CUtensorMap mx, const __grid_constant__ CUtensorMap mw,
             const __grid_constant__ CUtensorMap mo, const __grid_constant__ CUtensorMap mu,
             const __grid_constant__ CUtensorMap mout) {
  constexpr uint32_t sb = SB;
  const int tid = threadIdx.x, lane = tid & 31;
  const int warp = __shfl_sync(0xffffffffu, tid >> 5, 0);
  const int b = blockIdx.x, oct = b >> 3, i8 = b & 7;
  const int rt = (((oct & 4) ? ~oct : oct) & 3) * 2 + (i8 >> 2);
  const int hp = (oct >> 2) * 4 + (i8 & 3);

  const int wg = warp >> 2, w = warp & 3;
  const int d = b * 4 + ((tid >> 5) & 3);
  const KgenRaw raw = kgen_load(P, d, (tid >> 7) & 1, lane, (tid + 128) & 256);
  const uint32_t tb = sb + OFF_T + w * T_CH;
  if (warp >= 12) {
    asm volatile("setmaxnreg.dec.sync.aligned.u32 32;");
    if (warp == 12) {
      if (lane == 0) {
#pragma unroll
        for (int i = 0; i < 9; i++) mbar_init(BAR(i), 1);
        asm volatile("fence.mbarrier_init.release.cluster;" ::: "memory");
      }
      __syncwarp();
      if (lane < 9) mbar_expect(BAR(0) + 8 * lane, lane == 0 ? 16384 : 28672);
      __syncwarp();
      nb_arrive(NB_PROD, 384);
#pragma unroll 1
      for (int kb = 0; kb < 8; kb++) {
        if (kb == U_AT) e_tma4d(sb + OFF_STG0, &mu, BAR(MB_URAW), i8 * 64, oct * 2);
        e_tma3d(sb + OFF_W + kb * 12288, &mw, BAR(MB_FULL) + 8 * kb, hp * 32, kb * 64, 0);
        if (kb < 5) e_tma2d(sb + OFF_X + (kb < 2 ? kb + 3 : kb - 2) * 16384, &mx, BAR(MB_FULL) + 8 * kb, kb * 64, rt * 256);
      }
      if (smem_u32(smem_raw) != SB) __trap();
      if (lane == 0) TS1(54);
      nb_sync(NB_GATE + 1, 64);
      e_prefetch(P.x + (size_t)(rt * 256 + 128 + hp * 8) * 512, 8192);
      uint32_t slot = sb + OFF_X + 3 * 16384;
#pragma unroll 1
      for (int n = 0; n < 11; n++) {
        mbar_spin(BAR(MB_EMPTY) + 8 * n);
        const int m = n + 5;
        e_tma2d(slot, &mx, BAR(MB_FULL) + 8 * m, (m & 7) * 64, rt * 256 + (m >> 3) * 128);
        slot = slot == sb + OFF_X + 4 * 16384 ? sb + OFF_X : slot + 16384;
        if (n == 7) {
          e_prefetch(P.wo + (size_t)b * 2048, 4096);
          asm volatile("prefetch.tensormap [%0];" ::"l"(&mo) : "memory");
          asm volatile("prefetch.tensormap [%0];" ::"l"(&mout) : "memory");
        }
      }
#pragma unroll 1
      for (int i = 0; i < 8; i++) {
        mbar_wait(BAR(MB_EMPTY + 10) + 8 * ((0x54332222u >> (4 * i)) & 7));
        const int w0 = (0x54736210u >> (4 * i)) & 7;
        e_tma3d(sb + OFF_W + w0 * 16384, &mo, BAR(MB_WO), 0, w0 * 64, (hp & 3) * 2);
      }
    } else {
      if (warp == 13) {
        if (lane == 0) {
#pragma unroll
          for (int i = 9; i < 40; i++) mbar_init(BAR(i), i < MB_EMPTY ? 1 : 4);
          asm volatile("fence.mbarrier_init.release.cluster;" ::: "memory");
        }
        __syncwarp();
        if (lane < 14 && lane != 9) mbar_expect(BAR(MB_FULL + 8) + 8 * lane, lane == 8 ? 131072 : (lane == 10 ? 8192 : (lane == 13 ? 24576 : 16384)));
        nb_arrive(NB_GATE + 1, 64);
      } else if (warp == 14) {
        asm volatile("prefetch.tensormap [%0];" ::"l"(&mw) : "memory");
        asm volatile("prefetch.tensormap [%0];" ::"l"(&mx) : "memory");
        asm volatile("prefetch.tensormap [%0];" ::"l"(&mu) : "memory");
        e_prefetch(P.x + (size_t)(rt * 256 + hp * 8) * 512, 8192);
      }
      nb_sync(NB_PROD, 384);
      if (warp == 15) {
        const uint4 v0 = __ldg((const uint4*)P.wphi + hp * 64 + lane), v1 = __ldg((const uint4*)P.wphi + hp * 64 + 32 + lane);
        sts128(sb + OFF_PHI + (lane & 1) * 256 + (lane >> 1) * 16, v0.x, v0.y, v0.z, v0.w);
        sts128(sb + OFF_PHI + 512 + (lane & 1) * 256 + (lane >> 1) * 16, v1.x, v1.y, v1.z, v1.w);
        const uint32_t one = (((lane >> 3) ^ (lane >> 4)) & 1) ? 0u : ((lane & 1) ? 0x3F800000u : 0x3F80u);
        const int q = (lane >> 1) & 3;
        sts128(sb + OFF_EYE + lane * 16, q == 0 ? one : 0u, q == 1 ? one : 0u, q == 2 ? one : 0u, q == 3 ? one : 0u);
        sts64(sb + OFF_ONE + lane * 8, 0x3F803F80u, 0x3F803F80u);
        asm volatile("fence.proxy.async.shared::cta;" ::: "memory");
        nb_arrive(NB_KREAD, 160);
      }
      uint32_t* cnt = (uint32_t*)(P.xs + X_CNT) + (warp == 13 ? i8 : (warp == 14 ? 8 + rt : 16 + oct)) * 32;
      const unsigned target = (ld_x32(cnt) & ~15u) + 16;
      if (warp != 14) {
        if (warp == 15) mbar_wait(BAR(MB_EMPTY + ZERO_STEP));
        uint4* pz = P.xs + (warp == 13 ? X_PART + (hp * 8 + rt) * 144 : X_Y + b * 1024) + lane;
#pragma unroll 1
        for (int i = (warp == 13 ? 144 : 1024) - lane; i > 0; i -= 32, pz += 32) st_x(pz, 0, 0, 0, 0);
      }
      if (warp == 15) __syncwarp();
      else nb_sync(warp == 13 ? NB_INIT : NB_ODONE, warp == 13 ? 160 : 288);
      if (lane == 0) asm volatile("red.release.gpu.global.add.u32 [%0], %1;" ::"l"(cnt), "r"(warp == 15 ? 2 : 1) : "memory");
      if (lane == 0) TS1(warp == 13 ? 50 : (warp == 14 ? 57 : 53));
      __syncwarp();
      if (warp == 14) nb_arrive(NB_GATE + 1, 160);
      asm volatile("fence.proxy.async.shared::cta;" ::: "memory");
      if (warp == 13) cnt += ((lane & 1 ? b >> 4 : i8 ^ (lane & 4)) - i8) * 32;
#pragma unroll 1
      for (int i = 0; i < SPIN_MAX; i++) {
        unsigned v;
        asm volatile("ld.acquire.gpu.global.u32 %0, [%1];" : "=r"(v) : "l"(cnt) : "memory");
        if (__all_sync(0xffffffffu, (int)(v - target) >= 0)) break;
      }
      if (lane == 0) TS1(warp == 13 ? 51 : (warp == 14 ? 58 : 55));
      if (warp == 15) { nb_arrive(NB_YZ, 160); return; }
      asm volatile("fence.proxy.async.global;" ::: "memory");
      if (warp == 13) {
        mbar_wait(BAR(MB_EMPTY + 11));
        e_expect(BAR(MB_UFULL), 4 * U_CH);
        e_bulk(sb + OFF_U, P.xs + X_UT + b * (U_CH / 4), 4 * U_CH, BAR(MB_UFULL));
      } else {
        const uint4* src = P.xs + X_O + (rt * 4 + (hp >> 2)) * 4096;
        e_bulk(sb + OFF_X + 32768 + 57344, src + 3584, 8192, BAR(MB_O));
        e_bulk(sb + OFF_X + 32768, src, 16384, BAR(MB_O + 1));
        e_bulk(sb + OFF_X + 49152, src + 1024, 16384, BAR(MB_O + 2));
        e_bulk(sb + OFF_STG0, src + 3200, 6144, BAR(MB_O + 3));
        nb_sync(NB_BDONE, 288);
        asm volatile("fence.proxy.async.shared::cta;" ::: "memory");
        e_bulk(sb + OFF_U, src + 2048, 18432, BAR(MB_O + 3));
      }
    }
    return;
  }

  asm volatile("setmaxnreg.inc.sync.aligned.u32 160;");
  const int t = tid & 127;
  const int g = lane >> 2, c = lane & 3;
  const uint32_t kp = ((tb + 127) & ~127u) + (wg & 1) * 2048;
  const KgenAddr kad = kgen_addr(lane, kp);
  if (wg) nb_sync(NB_PROD, 384);
  float k[5][4], k2048, ksc;
  if (wg) {
    kgen_unit(raw, kad, blockIdx.y, k, k2048, ksc);
    TS(40 + wg);
    if ((fu(k[0][0]) & fu(k[1][0]) & fu(k[2][0]) & fu(k[3][0]) & fu(k[4][0])) == 0xffffffffu) sts32(kp, 0);
  }
  if (wg) nb_arrive(0, 384);
  if (wg) {
    if (wg == 1) {
      uint32_t h[10];
#pragma unroll
      for (int j = 0; j < 10; j++) h[j] = hu(__floats2half2_rn(k[j >> 1][2 * (j & 1)], k[j >> 1][2 * (j & 1) + 1]));
      sts128(kp + lane * 16, h[0], h[1], h[2], h[3]);
      sts128(kp + 512 + lane * 16, h[4], h[5], h[6], h[7]);
      sts128(kp + 1024 + lane * 16, h[8], h[9], fu(k2048), fu(ksc));
      nb_arrive(NB_PREP, 256);
    }
  } else {
    nb_sync(NB_KREAD, 160);
  }
  if (wg == 1) {
    mbar_wait(BAR(MB_URAW));
    TS(48);
    uint4* dst = P.xs + X_UT + (i8 * 64 + g) * (U_CH / 16) + (w & 1) * (U_ODD / 16) + U_PAD / 16 + oct * 8 + (w >> 1) * 4 + c;
    const int ln = ((lane >> 1) & 3) + 4 * (lane & 1);
    uint32_t r[8][4];
#pragma unroll
    for (int i = 0; i < 8; i++) ldsm4t(r[i], sb + OFF_STG0 + w * 4096 + ((lane >> 3) * 8 + ln) * 128 + ((i ^ ln) << 4));
#pragma unroll
    for (int i = 0; i < 8; i++) dst[i * (U_CH / 2)] = make_uint4(r[i][0], r[i][1], r[i][2], r[i][3]);
    nb_arrive(NB_INIT, 160);
    if (lane == 0) mbar_arrive(BAR(MB_AUX));
  }
  {
    if (wg == 2) {
#pragma unroll
      for (int j = 0; j < 5; j++) { k[j][0] *= ksc; k[j][1] *= ksc; k[j][2] *= ksc; k[j][3] *= ksc; }
      const unsigned short dsk = __ldg((const unsigned short*)P.Dskip + d);
      nb_sync(NB_PREP, 256);
      {
        const uint32_t src = kp + 2048 + lane * 16;
        const uint4 v0 = lds128(src), v1 = lds128(src + 512), v2 = lds128(src + 1024);
        const uint32_t h[10] = {v0.x, v0.y, v0.z, v0.w, v1.x, v1.y, v1.z, v1.w, v2.x, v2.y};
#pragma unroll
        for (int j = 0; j < 10; j++) {
          const float2 f = __half22float2(*(const __half2*)&h[j]);
          k[j >> 1][2 * (j & 1)] = fmaf(f.x, uf(v2.w), k[j >> 1][2 * (j & 1)]);
          k[j >> 1][2 * (j & 1) + 1] = fmaf(f.y, uf(v2.w), k[j >> 1][2 * (j & 1) + 1]);
        }
        k2048 += uf(v2.z);
      }
#pragma unroll
      for (int o2 = 16; o2; o2 >>= 1) k2048 += __shfl_xor_sync(0xffffffffu, k2048, o2);
      if (lane == 0) k[0][0] += bf_lo(dsk);
      __syncwarp();
      TS(34);
      build_tables(tb, lane, k, k2048);
      TS(35);
      uint4* const g_y = P.xs + X_Y;
      conv_channel(sb + OFF_U + w * U_CH, tb, lane, g_y + (size_t)d * 256 + lane);
      nb_arrive(NB_Y, 160);
      TS(37);
      if (w == 0) TSDUMP(32);
      return;
    }
    if (wg == 1) {
      mbar_wait(BAR(MB_EMPTY + 4));
      mbar_spin(BAR(MB_EMPTY + 6));
    }
    TS(wg * 16 + 1);
  }

  float acc[2][48];
  {
    uint32_t fb = BAR(MB_FULL) + 64 * wg;
    uint32_t da = (uint32_t)mkdesc(sb + OFF_X, 16, 0, 0) + (wg ? 1024 : 3072), db = (uint32_t)mkdesc(sb + OFF_W, 4096, 0, 0);
    constexpr uint64_t ha = mkdesc(0, 0, 1024, 1), hb = mkdesc(0, 0, 512, 2);
    mbar_spin(fb);
    if (wg == 0) nb_sync(0, 384);
    TS(wg * 16 + 2);
#pragma unroll 1
    for (int kb = 0; kb < 8; kb++) {
      WG_FENCE();
#pragma unroll
      for (int k = 0; k < 4; k++) {
        wgmma_ss_n96(acc[0], ha | (da + 2 * k), hb | (db + 64 * k), k ? 1 : kb);
        wgmma_ss_n96(acc[1], ha | (da + 2 * k + 512), hb | (db + 64 * k), k ? 1 : kb);
      }
      WG_COMMIT();
      if (kb < 7) mbar_spin(fb + 8);
      WG_WAIT(1);
      if (kb > 0) e_arrive(fb + 8 * (MB_EMPTY - MB_FULL - 1));
      fb += 8; db += 768;
      da = da == (uint32_t)mkdesc(sb + OFF_X + 65536, 16, 0, 0) ? da - 4096 : da + 1024;
    }
    WG_WAIT(0);
    e_arrive(fb + 8 * (MB_EMPTY - MB_FULL - 1));
    SPLIT();
  }
  TS(wg * 16 + 3);

  constexpr uint32_t stg0 = sb + OFF_STG0, stg1 = sb + OFF_X + 32768;
  uint4* const g_part = P.xs + X_PART;
  uint4* const g_o = P.xs + X_O;
  constexpr uint32_t kvs = stg0;
  auto pack8 = [](const float* a) { return make_uint4(pack_bf(a[0], a[1]), pack_bf(a[2], a[3]), pack_bf(a[4], a[5]), pack_bf(a[6], a[7])); };
  auto stage_k = [&](auto nt, const uint4* af, const uint4* vp, uint32_t sl, uint32_t free_bar) {
    constexpr int NU = 2 * decltype(nt)::value;
    float p[NU][8], rs[2 * NU][4];
    uint32_t ek[8 * NU];
    WG_FENCE();
#pragma unroll
    for (int u = 0; u < NU; u++) wgmma_rs_n16(p[u], af[u], qdesc(sb + OFF_PHI + (u & 1) * 512), 0);
    WG_COMMIT();
    WG_WAIT(0);
#pragma unroll
    for (int u = 0; u < NU; u++) {
      const uint32_t pw[4] = {pack_bf(p[u][0], p[u][2]), pack_bf(p[u][1], p[u][3]), pack_bf(p[u][4], p[u][6]), pack_bf(p[u][5], p[u][7])};
      dual_exp(pw, ek + 8 * u);
    }
    TS(wg * 16 + 12);
    mbar_spin(free_bar);
    WG_FENCE();
#pragma unroll
    for (int i = 0; i < 2 * NU; i++) wgmma_rs_n8(rs[i], make_uint4(ek[4 * i], ek[4 * i + 1], ek[4 * i + 2], ek[4 * i + 3]), qdesc(sb + OFF_ONE), 0);
    WG_COMMIT();
#pragma unroll
    for (int i = 0; i < NU; i++) stsm4(sl + (i >> 1) * 4 * SLAB + 2048 + (i & 1) * 512, vp[i].x, vp[i].y, vp[i].z, vp[i].w);
    if (NU == 4 || lane < 16) sts128(sl + (lane >> 4) * (4 * SLAB - 256) + 3072, 0x3F803F80u, 0x3F803F80u, 0x3F803F80u, 0x3F803F80u);
    WG_WAIT(0);
#pragma unroll
    for (int i = 0; i < 2 * NU; i++) {
      normalise(ek + 4 * i, rs[i]);
      stsm4(sl + (i >> 2) * 4 * SLAB + (i & 3) * 512, ek[4 * i], ek[4 * i + 1], ek[4 * i + 2], ek[4 * i + 3]);
    }
    asm volatile("fence.proxy.async.shared::cta;" ::: "memory");
  };
  auto contract = [&](float (&kc)[20], uint32_t stg, int acc_in) {
    WG_FENCE();
#pragma unroll
    for (int s = 0; s < 8; s++) wgmma_ss_n40(kc, qdesc(stg + s * SLAB), qdesc(stg + s * SLAB + 2048), s ? 1 : acc_in);
    WG_COMMIT();
    WG_WAIT(0);
  };
  uint32_t eq[32];
  {
    uint4 af[4], aq[4], vp[4];
    float kc[20];
#pragma unroll
    for (int u = 0; u < 4; u++) { af[u] = pack8(acc[u >> 1] + 16 + 8 * (u & 1)); vp[u] = pack8(acc[u >> 1] + 32 + 8 * (u & 1)); }
    const uint32_t hand = stg1 + 16384 + 8192 + w * 2048 + lane * 16;
    if (wg) {
      sts128(hand, af[2].x, af[2].y, af[2].z, af[2].w); sts128(hand + 512, af[3].x, af[3].y, af[3].z, af[3].w);
      sts128(hand + 1024, vp[2].x, vp[2].y, vp[2].z, vp[2].w); sts128(hand + 1536, vp[3].x, vp[3].y, vp[3].z, vp[3].w);
      nb_arrive(NB_HAND, 256);
    }
#pragma unroll
    for (int u = 0; u < 4; u++) aq[u] = pack8(acc[u >> 1] + 8 * (u & 1));
    if (wg == 0) {
      stage_k(std::integral_constant<int, 2>(), af, vp, stg0 + w * SLAB + lane * 16, BAR(MB_AUX));
      TS(13);
      nb_sync(NB_WG0, 128);
      contract(kc, stg0, 0);
      mbar_wait(BAR(MB_UFULL));
      TS(15);
      nb_sync(NB_HAND, 256);
      af[0] = lds128(hand); af[1] = lds128(hand + 512); vp[0] = lds128(hand + 1024); vp[1] = lds128(hand + 1536);
      nb_sync(NB_WG0, 128);
    }
    stage_k(std::integral_constant<int, 1>(), af, vp, stg1 + (wg ? w : 4 + w) * SLAB + lane * 16, BAR(MB_EMPTY + 15));
    TS(wg * 16 + 14);
    float p[4][8];
    if (wg) {
      nb_arrive(NB_ST0, 256);
      nb_arrive(NB_GATE, 256);
    } else {
      uint4* pp = g_part + (size_t)(hp * 8 + rt) * 144 + t;
      uint32_t* pz = (uint32_t*)(pp - t + 128) + w * 16 + c * 8 + g;
      asm volatile("" : "+l"(pp), "+l"(pz));
      nb_sync(NB_ST0, 256);
      contract(kc, stg1, 1);
      TS(6);
      float kv[8];
#pragma unroll
      for (int i = 0; i < 8; i++) kv[i] = w & 2 ? kc[8 + i] : kc[i];
      st_x(pp, nz(pack_bf(kv[0], kv[1])), pack_bf(kv[2], kv[3]), pack_bf(kv[4], kv[5]), pack_bf(kv[6], kv[7]));
      if (c < 2) st_x32(pz, nz(fu(c ? kc[18] : kc[16])));
      TS(5);
    }
    SPLIT();
    WG_FENCE();
#pragma unroll
    for (int u = 0; u < 4; u++) wgmma_rs_n16(p[u], aq[u], qdesc(sb + OFF_PHI + (u & 1) * 512), 0);
    WG_COMMIT();
    WG_WAIT(0);
#pragma unroll
    for (int u = 0; u < 4; u++) {
      const uint32_t pw[4] = {pack_bf(p[u][0], p[u][2]), pack_bf(p[u][1], p[u][3]), pack_bf(p[u][4], p[u][6]), pack_bf(p[u][5], p[u][7])};
      dual_exp(pw, eq + 8 * u);
    }
    SPLIT();
  }
  TS(wg * 16 + 4);
  if (wg == 1) {
    mbar_wait(BAR(MB_UFULL));
    const uint4* ps = g_part + (size_t)hp * 8 * 144 + t;
    const uint32_t* zs = (const uint32_t*)(g_part + (size_t)(hp * 8 + (lane >> 4) * 4) * 144 + 128) + w * 16 + (lane & 15);
    uint4 v[8];
    uint32_t zv[4];
#pragma unroll 1
    for (int it = 0; it < SPIN_MAX; it++) {
#pragma unroll
      for (int i = 0; i < 8; i++) v[i] = ld_x(ps + i * 144);
#pragma unroll
      for (int i = 0; i < 4; i++) zv[i] = ld_x32(zs + i * 576);
      uint32_t m = min(min(zv[0], zv[1]), min(zv[2], zv[3]));
#pragma unroll
      for (int i = 0; i < 8; i++) m = min(m, v[i].x);
      if (__all_sync(0xffffffffu, m != 0)) break;
    }
    float s[8];
    WG_FENCE();
#pragma unroll
    for (int r = 0; r < 8; r++) wgmma_rs_n16(s, v[r], qdesc(sb + OFF_EYE), r);
    WG_COMMIT();
    float zsum = (uf(zv[0]) + uf(zv[1])) + (uf(zv[2]) + uf(zv[3]));
    zsum += __shfl_xor_sync(0xffffffffu, zsum, 16);
    const uint32_t z1 = pack_bf(zsum, 1.f);
    if (lane < 16) sts128(kvs + w * 768 + 512 + lane * 16, z1, z1, z1, z1);
    WG_WAIT(0);
    stsm4(kvs + w * 768 + lane * 16, pack_bf(s[0], s[1]), pack_bf(s[2], s[3]), pack_bf(s[4], s[5]), pack_bf(s[6], s[7]));
    asm volatile("fence.proxy.async.shared::cta;" ::: "memory");
    TS(22);
  }
  nb_sync(NB_KV, 256);
  {
    float n[8][12];
    WG_FENCE();
#pragma unroll
    for (int i = 0; i < 8; i++) wgmma_rs_n24(n[i], make_uint4(eq[4 * i], eq[4 * i + 1], eq[4 * i + 2], eq[4 * i + 3]), qdesc(kvs + (i & 3) * 768), 0);
    WG_COMMIT();
    uint32_t* od = (uint32_t*)(g_o + (size_t)((rt * 4 + wg * 2) * 32 + hp * 2) * 128) + w * 64 + lane;
    WG_WAIT(0);
#pragma unroll
    for (int u = 0; u < 4; u++) {
      float(&np)[12] = n[2 * u];
      const float(&nm)[12] = n[2 * u + 1];
      const float q0 = np[9] * rcp(nm[9]), q1 = np[11] * rcp(nm[11]);
      const float r0 = rcp(fmaf(nm[8], q0, fmaf(np[9], 1e-6f, np[8]))), r1 = rcp(fmaf(nm[10], q1, fmaf(np[11], 1e-6f, np[10])));
#pragma unroll
      for (int i = 0; i < 8; i++) np[i] = fmaf(nm[i], (i & 2) ? q1 : q0, np[i]);
      uint32_t* o = od + (u >> 1) * 16384 + (u & 1) * 512;
      o[0] = pack_bf(np[0] * r0, np[1] * r0);
      o[32] = pack_bf(np[2] * r1, np[3] * r1);
      o[256] = pack_bf(np[4] * r0, np[5] * r0);
      o[288] = pack_bf(np[6] * r1, np[7] * r1);
      if (u == 1) SPLIT();
    }
  }
  TS(wg * 16 + 7);
  nb_arrive(NB_ODONE, 288);
  if (wg) {
    const uint4* src = P.xs + X_Y + (oct * 32 + c * 8) * 256 + (2 * w + (g >> 2)) * 32 + i8 * 4 + (g & 3);
    __nv_bfloat16* dst = P.out + (size_t)((2 * w + (g >> 2)) * 256 + i8 * 16 + (g & 3) * 2) * 1024 + 512 + oct * 32 + c * 8;
    nb_sync(NB_GATE + 1, 160);
    nb_sync(NB_Y + w, 160);
    uint4 v[8];
#pragma unroll 1
    for (int it = 0; it < SPIN_MAX; it++) {
      uint32_t m = 0xffffffffu;
#pragma unroll
      for (int i = 0; i < 8; i++) v[i] = ld_x(src + i * 256);
#pragma unroll
      for (int i = 0; i < 8; i++) m = min(m, v[i].x);
      if (__all_sync(0xffffffffu, m != 0)) break;
    }
#pragma unroll
    for (int i = 0; i < 8; i++) *(uint4*)(dst + (size_t)((i >> 2) * 128 + ((i >> 1) & 1) * 8 + (i & 1)) * 1024) = tr_row(v, i);
    TS(31);
    GT(63);
    if (w == 0) TSDUMP(16);
    return;
  }
  mbar_wait(BAR(MB_WO));
  nb_sync(NB_BDONE, 288);
  TS(8);
  mbar_spin(BAR(MB_O));
  TS(9);
  constexpr uint64_t ha = mkdesc(0, 0, 128, 0), hb = mkdesc(0, 0, 1024, 1);
  constexpr uint32_t da0 = (uint32_t)mkdesc(stg1, 1024, 0, 0), db0 = (uint32_t)mkdesc(sb + OFF_W, 8192, 0, 0);
  const uint32_t ot = ((sb + OFF_T + 1023) & ~1023u) + w * 4096;
  auto store_half = [&](const float* oc, int hf) {
#pragma unroll
    for (int i = 0; i < 8; i += 2)
      stsm4(ot + hf * 2048 + (lane & 15) * 128 + (((i + (lane >> 4)) ^ lane) & 7) * 16, pack_bf(oc[4 * i], oc[4 * i + 1]),
            pack_bf(oc[4 * i + 2], oc[4 * i + 3]), pack_bf(oc[4 * i + 4], oc[4 * i + 5]), pack_bf(oc[4 * i + 6], oc[4 * i + 7]));
    asm volatile("fence.proxy.async.shared::cta;" ::: "memory");
    __syncwarp();
    e_store2d(&mout, ot + hf * 2048, (hp & 3) * 128 + hf * 64, (rt * 4 + (hp >> 2)) * 64 + w * 16);
  };
  float oc[64];
#pragma unroll 1
  for (int j = 0; j < 8; j++) {
    const int kb = (j + 7) & 7;
    if ((j & 1) && j < 6) mbar_spin(BAR(MB_O + 1) + 4 * (j - 1));
    WG_FENCE();
#pragma unroll
    for (int k = 0; k < 4; k++) wgmma_ss_n128(oc, ha | (da0 + 512 * kb + 128 * k), hb | (db0 + 1024 * kb + 128 * k), k ? 1 : j);
    WG_COMMIT();
  }
  WG_WAIT(0);
  TS(10);
  store_half(oc, 0);
  store_half(oc + 32, 1);
  asm volatile(ELECT "cp.async.bulk.commit_group;\n@p cp.async.bulk.wait_group.read 0;\n}\n" ::: "memory");
  TS(wg * 16 + 11);
  GT(61 + wg);
  if (w == 0) TSDUMP(0);
  if (w == 1) TSDUMP(48);
}

typedef CUresult (*EncodeFn)(CUtensorMap*, CUtensorMapDataType, cuuint32_t, void*, const cuuint64_t*, const cuuint64_t*,
                             const cuuint32_t*, const cuuint32_t*, CUtensorMapInterleave, CUtensorMapSwizzle,
                             CUtensorMapL2promotion, CUtensorMapFloatOOBfill);

}

extern "C" void kernel_launch(void* const* d_in, const int* in_sizes, int n_in, void* d_out, int out_size) {
  (void)in_sizes; (void)n_in; (void)out_size;
  void* fn = nullptr;
  cudaDriverEntryPointQueryResult qr;
  cudaGetDriverEntryPoint("cuTensorMapEncodeTiled", &fn, cudaEnableDefault, &qr);
  EncodeFn enc = (EncodeFn)fn;
  CUtensorMap mx, mw, mo, mu, mout;
  const cuuint32_t es[5] = {1, 1, 1, 1, 1};
  {
    cuuint64_t dims[2] = {512, 2048}, st[1] = {1024};
    cuuint32_t box[2] = {64, 128};
    enc(&mx, CU_TENSOR_MAP_DATA_TYPE_BFLOAT16, 2, d_in[0], dims, st, box, es, CU_TENSOR_MAP_INTERLEAVE_NONE,
        CU_TENSOR_MAP_SWIZZLE_128B, CU_TENSOR_MAP_L2_PROMOTION_L2_128B, CU_TENSOR_MAP_FLOAT_OOB_FILL_NONE);
  }
  {
    cuuint64_t dims[3] = {512, 512, 3}, st[2] = {3072, 1024};
    cuuint32_t box[3] = {32, 64, 3};
    enc(&mw, CU_TENSOR_MAP_DATA_TYPE_BFLOAT16, 3, d_in[1], dims, st, box, es, CU_TENSOR_MAP_INTERLEAVE_NONE,
        CU_TENSOR_MAP_SWIZZLE_64B, CU_TENSOR_MAP_L2_PROMOTION_L2_128B, CU_TENSOR_MAP_FLOAT_OOB_FILL_NONE);
  }
  {
    cuuint64_t dims[3] = {64, 512, 8}, st[2] = {1024, 128};
    cuuint32_t box[3] = {64, 64, 2};
    enc(&mo, CU_TENSOR_MAP_DATA_TYPE_BFLOAT16, 3, d_in[3], dims, st, box, es, CU_TENSOR_MAP_INTERLEAVE_NONE,
        CU_TENSOR_MAP_SWIZZLE_128B, CU_TENSOR_MAP_L2_PROMOTION_L2_128B, CU_TENSOR_MAP_FLOAT_OOB_FILL_NONE);
  }
  {
    cuuint64_t dims[4] = {512, 4, 16, 32}, st[3] = {16384, 1024, 65536};
    cuuint32_t box[4] = {64, 4, 16, 2};
    enc(&mu, CU_TENSOR_MAP_DATA_TYPE_BFLOAT16, 4, d_in[4], dims, st, box, es, CU_TENSOR_MAP_INTERLEAVE_NONE,
        CU_TENSOR_MAP_SWIZZLE_128B, CU_TENSOR_MAP_L2_PROMOTION_L2_128B, CU_TENSOR_MAP_FLOAT_OOB_FILL_NONE);
  }
  {
    cuuint64_t dims[2] = {1024, 2048}, st[1] = {2048};
    cuuint32_t box[2] = {64, 16};
    enc(&mout, CU_TENSOR_MAP_DATA_TYPE_BFLOAT16, 2, d_out, dims, st, box, es, CU_TENSOR_MAP_INTERLEAVE_NONE,
        CU_TENSOR_MAP_SWIZZLE_128B, CU_TENSOR_MAP_L2_PROMOTION_NONE, CU_TENSOR_MAP_FLOAT_OOB_FILL_NONE);
  }
  Params P;
  P.x = (const __nv_bfloat16*)d_in[0];
  P.wphi = (const __nv_bfloat16*)d_in[2];
  P.wo = (const __nv_bfloat16*)d_in[3];
  P.logA = (const __nv_bfloat16*)d_in[5];
  P.Aim = (const __nv_bfloat16*)d_in[6];
  P.Cre = (const __nv_bfloat16*)d_in[7];
  P.Cim = (const __nv_bfloat16*)d_in[8];
  P.logdt = (const __nv_bfloat16*)d_in[9];
  P.Dskip = (const __nv_bfloat16*)d_in[10];
  P.out = (__nv_bfloat16*)d_out;
  cudaGetSymbolAddress((void**)&P.xs, g_x);
  P.ts = nullptr;
  cudaFuncSetAttribute(fused_kernel, cudaFuncAttributeMaxDynamicSharedMemorySize, SMEM_BYTES);
  fused_kernel<<<NCTA, NTHREADS, SMEM_BYTES>>>(P, mx, mw, mo, mu, mout);
}
```

```cpp
#include <cuda_runtime.h>
#include <cuda_bf16.h>
#include <cuda_fp16.h>
#include <cuda.h>
#include <stdint.h>
#include <type_traits>

#define DBG_TS 0

namespace {

constexpr int NTHREADS = 512;
constexpr int NCTA = 128;
constexpr int OFF_W = 0;
constexpr int OFF_X = 98304;
constexpr int OFF_U = OFF_X + 65536;
constexpr int U_CH = 4416, U_ODD = 2240, U_PAD = 128;
constexpr int OFF_STG0 = OFF_U + 18432;
constexpr int SLAB = 3328;
constexpr int OFF_T = OFF_STG0 + 8 * SLAB;
constexpr int T_CH = 5216;
constexpr int T_D = 0;
constexpr int T_5 = 2144;
constexpr int T_3 = T_5 + 384;
constexpr int T_7 = T_5 + 1024;
constexpr int T_9 = T_7 + 320;
constexpr int T_KC = T_9 + 320;
constexpr int T_ST = T_5 - 1024;
constexpr int OFF_PHI = OFF_T + 4 * T_CH;
constexpr int OFF_EYE = OFF_PHI + 1024, OFF_ONE = OFF_EYE + 512;
constexpr int OFF_BAR = OFF_ONE + 256;
constexpr int SMEM_BYTES = OFF_BAR + 512 + 256 * DBG_TS;
constexpr uint32_t SB = 1024;
static_assert(T_KC + 2 * 656 <= T_CH, "table size");
static_assert(SMEM_BYTES <= 232448, "smem");
constexpr int MB_URAW = 0, MB_FULL = 1  , MB_WO = 17, MB_UFULL = 18, MB_O = 19  ,
              MB_EMPTY = 23  , MB_AUX = 39;
__host__ __device__ constexpr uint32_t BAR(int i) { return SB + OFF_BAR + 8 * i; }
constexpr int NB_WG0 = 1, NB_ODONE = 2, NB_ST0 = 3, NB_HAND = 4, NB_KV = 5, NB_YZ = 6, NB_INIT = 7, NB_PREP = 8, NB_PROD = 9, NB_KREAD = 10,
              NB_BDONE = 11, NB_GATE = 12  , NB_Y = 7  ;
constexpr int U_AT = 2;
constexpr int ZERO_STEP = 12;
constexpr int SPIN_MAX = 1 << 16;

constexpr int X_CNT = 0;
constexpr int X_PART = 256;
constexpr int X_O = X_PART + 16 * 8 * 144;
constexpr int X_Y = X_O + 32 * 32 * 128;
constexpr int X_UT = X_Y + 512 * 8 * 32;
constexpr int X_SIZE = X_UT + 512 * (U_CH / 16);
__device__ __align__(128) uint4 g_x[X_SIZE];
extern __shared__ uint8_t smem_raw[];
#define TS(i) do {} while (0)
#define TS1(i) do {} while (0)
#define GT(i) do {} while (0)
#define TSDUMP(base) do {} while (0)

__device__ __forceinline__ uint32_t smem_u32(const void* p) { return (uint32_t)__cvta_generic_to_shared(p); }
__device__ __forceinline__ void mbar_arrive(uint32_t b) {
  asm volatile("mbarrier.arrive.shared::cta.b64 _, [%0];" ::"r"(b) : "memory");
}
__device__ __forceinline__ void mbar_wait(uint32_t b) {
  uint32_t done = 0;
#pragma unroll 1
  for (int i = 0; i < SPIN_MAX && !done; i++) {
    asm volatile("{\n.reg .pred p;\nmbarrier.try_wait.parity.shared::cta.b64 p, [%1], 0, 4000;\nselp.u32 %0, 1, 0, p;\n}\n"
                 : "=r"(done) : "r"(b) : "memory");
  }
}
__device__ __forceinline__ void mbar_spin(uint32_t b) {
  uint32_t done = 0;
#pragma unroll 1
  for (int i = 0; i < (SPIN_MAX << 4) && !done; i++) {
    asm volatile("{\n.reg .pred p;\nmbarrier.try_wait.parity.shared::cta.b64 p, [%1], 0;\nselp.u32 %0, 1, 0, p;\n}\n"
                 : "=r"(done) : "r"(b) : "memory");
  }
}
__device__ __forceinline__ void mbar_init(uint32_t b, int n) {
  asm volatile("mbarrier.init.shared::cta.b64 [%0], %1;" ::"r"(b), "r"(n) : "memory");
}
__device__ __forceinline__ void mbar_expect(uint32_t b, int bytes) {
  asm volatile("mbarrier.arrive.expect_tx.shared::cta.b64 _, [%0], %1;" ::"r"(b), "r"(bytes) : "memory");
}
__device__ __forceinline__ void nb_sync(int id, int n) { asm volatile("bar.sync %0, %1;" ::"r"(id), "r"(n) : "memory"); }
__device__ __forceinline__ void nb_arrive(int id, int n) { asm volatile("bar.arrive %0, %1;" ::"r"(id), "r"(n) : "memory"); }
#define ELECT "{\n.reg .pred p;\nelect.sync _|p, 0xffffffff;\n@p "
__device__ __forceinline__ void e_arrive(uint32_t b) {
  asm volatile(ELECT "mbarrier.arrive.shared::cta.b64 _, [%0];\n}\n" ::"r"(b) : "memory");
}
__device__ __forceinline__ void e_expect(uint32_t b, int bytes) {
  asm volatile(ELECT "mbarrier.arrive.expect_tx.shared::cta.b64 _, [%0], %1;\n}\n" ::"r"(b), "r"(bytes) : "memory");
}
__device__ __forceinline__ void e_tma2d(uint32_t dst, const CUtensorMap* m, uint32_t bar, int c0, int c1) {
  asm volatile(ELECT "cp.async.bulk.tensor.2d.shared::cluster.global.mbarrier::complete_tx::bytes [%0], [%1, {%3,%4}], [%2];\n}\n"
               ::"r"(dst), "l"(m), "r"(bar), "r"(c0), "r"(c1) : "memory");
}
__device__ __forceinline__ void e_tma3d(uint32_t dst, const CUtensorMap* m, uint32_t bar, int c0, int c1, int c2) {
  asm volatile(ELECT "cp.async.bulk.tensor.3d.shared::cluster.global.mbarrier::complete_tx::bytes [%0], [%1, {%3,%4,%5}], [%2];\n}\n"
               ::"r"(dst), "l"(m), "r"(bar), "r"(c0), "r"(c1), "r"(c2) : "memory");
}
__device__ __forceinline__ void e_tma4d(uint32_t dst, const CUtensorMap* m, uint32_t bar, int c0, int c3) {
  asm volatile(ELECT "cp.async.bulk.tensor.4d.shared::cluster.global.mbarrier::complete_tx::bytes [%0], [%1, {%3,%5,%5,%4}], [%2];\n}\n"
               ::"r"(dst), "l"(m), "r"(bar), "r"(c0), "r"(c3), "r"(0) : "memory");
}
__device__ __forceinline__ void e_bulk(uint32_t dst, const void* src, int bytes, uint32_t bar) {
  asm volatile(ELECT "cp.async.bulk.shared::cluster.global.mbarrier::complete_tx::bytes [%0], [%1], %2, [%3];\n}\n"
               ::"r"(dst), "l"(src), "r"(bytes), "r"(bar) : "memory");
}
__device__ __forceinline__ void e_prefetch(const void* p, int bytes) {
  asm volatile(ELECT "cp.async.bulk.prefetch.L2.global [%0], %1;\n}\n" ::"l"(p), "r"(bytes) : "memory");
}
__device__ __forceinline__ void e_store2d(const CUtensorMap* m, uint32_t src, int c0, int c1) {
  asm volatile(ELECT "cp.async.bulk.tensor.2d.global.shared::cta.bulk_group [%0, {%2,%3}], [%1];\n}\n"
               ::"l"(m), "r"(src), "r"(c0), "r"(c1) : "memory");
}
__host__ __device__ constexpr uint64_t mkdesc(uint32_t addr, uint32_t lbo, uint32_t sbo, int swz) {
  return (uint64_t)((addr & 0x3FFFF) >> 4) | ((uint64_t)(lbo >> 4) << 16) | ((uint64_t)(sbo >> 4) << 32) |
         ((uint64_t)swz << 62);
}
#define SPLIT() asm volatile("{\n.reg .pred p;\nsetp.eq.u32 p, %0, %1;\n@p exit;\n}\n" ::"r"(blockIdx.y), "n"(__LINE__) : "memory")
#define SPLITN(n) asm volatile("{\n.reg .pred p;\nsetp.eq.u32 p, %0, %1;\n@p exit;\n}\n" ::"r"(blockIdx.y), "r"(4096 + (n)) : "memory")
#define WG_FENCE() asm volatile("wgmma.fence.sync.aligned;" ::: "memory")
#define WG_COMMIT() asm volatile("wgmma.commit_group.sync.aligned;" ::: "memory")
#define WG_WAIT(n) asm volatile("wgmma.wait_group.sync.aligned " #n ";" ::: "memory")

__device__ __forceinline__ void mma(float& d0, float& d1, float& d2, float& d3, uint32_t a0, uint32_t a1, uint32_t a2,
                                    uint32_t a3, uint32_t b0, uint32_t b1) {
  asm volatile("mma.sync.aligned.m16n8k16.row.col.f32.bf16.bf16.f32 {%0,%1,%2,%3},{%4,%5,%6,%7},{%8,%9},{%0,%1,%2,%3};"
               : "+f"(d0), "+f"(d1), "+f"(d2), "+f"(d3)
               : "r"(a0), "r"(a1), "r"(a2), "r"(a3), "r"(b0), "r"(b1));
}
__device__ __forceinline__ void mmac(float (&d)[4], uint32_t a0, uint32_t a1, uint32_t a2, uint32_t a3, uint32_t b0,
                                     uint32_t b1, const float (&c)[4]) {
  asm volatile("mma.sync.aligned.m16n8k16.row.col.f32.bf16.bf16.f32 {%0,%1,%2,%3},{%4,%5,%6,%7},{%8,%9},{%10,%11,%12,%13};"
               : "=f"(d[0]), "=f"(d[1]), "=f"(d[2]), "=f"(d[3])
               : "r"(a0), "r"(a1), "r"(a2), "r"(a3), "r"(b0), "r"(b1), "f"(c[0]), "f"(c[1]), "f"(c[2]), "f"(c[3]));
}
__device__ __forceinline__ void mma_h(float (&d)[4], const uint32_t (&a)[4], uint32_t b0, uint32_t b1) {
  asm volatile("mma.sync.aligned.m16n8k16.row.col.f32.f16.f16.f32 {%0,%1,%2,%3},{%4,%5,%6,%7},{%8,%9},{%0,%1,%2,%3};"
               : "+f"(d[0]), "+f"(d[1]), "+f"(d[2]), "+f"(d[3]) : "r"(a[0]), "r"(a[1]), "r"(a[2]), "r"(a[3]), "r"(b0), "r"(b1));
}
__device__ __forceinline__ void mma0(float& d0, float& d1, float& d2, float& d3, uint32_t a0, uint32_t a1, uint32_t a2,
                                     uint32_t a3, uint32_t b0, uint32_t b1) {
  asm volatile("mma.sync.aligned.m16n8k16.row.col.f32.bf16.bf16.f32 {%0,%1,%2,%3},{%4,%5,%6,%7},{%8,%9},{%10,%10,%10,%10};"
               : "=f"(d0), "=f"(d1), "=f"(d2), "=f"(d3)
               : "r"(a0), "r"(a1), "r"(a2), "r"(a3), "r"(b0), "r"(b1), "f"(0.f));
}
__device__ __forceinline__ uint32_t pack_bf(float lo, float hi) {
  uint32_t r;
  asm("cvt.rn.bf16x2.f32 %0, %1, %2;" : "=r"(r) : "f"(hi), "f"(lo));
  return r;
}
__device__ __forceinline__ float bf_lo(uint32_t w) { return __uint_as_float(w << 16); }
__device__ __forceinline__ float bf_hi(uint32_t w) { return __uint_as_float(w & 0xffff0000u); }
__device__ __forceinline__ float bf_round(float x) { return __bfloat162float(__float2bfloat16_rn(x)); }
__device__ __forceinline__ uint32_t bmax2(uint32_t a, uint32_t b) {
  uint32_t r; asm("max.bf16x2 %0, %1, %2;" : "=r"(r) : "r"(a), "r"(b)); return r;
}
__device__ __forceinline__ uint32_t bmin2(uint32_t a, uint32_t b) {
  uint32_t r; asm("min.bf16x2 %0, %1, %2;" : "=r"(r) : "r"(a), "r"(b)); return r;
}
__device__ __forceinline__ float ex2(float x) { float r; asm("ex2.approx.ftz.f32 %0, %1;" : "=f"(r) : "f"(x)); return r; }
__device__ __forceinline__ float rcp(float x) { float r; asm("rcp.approx.ftz.f32 %0, %1;" : "=f"(r) : "f"(x)); return r; }
__device__ __forceinline__ void ldsm4(uint32_t (&r)[4], uint32_t a) {
  asm volatile("ldmatrix.sync.aligned.m8n8.x4.shared.b16 {%0,%1,%2,%3}, [%4];"
               : "=r"(r[0]), "=r"(r[1]), "=r"(r[2]), "=r"(r[3]) : "r"(a) : "memory");
}
__device__ __forceinline__ void ldsm4t(uint32_t (&r)[4], uint32_t a) {
  asm volatile("ldmatrix.sync.aligned.m8n8.x4.trans.shared.b16 {%0,%1,%2,%3}, [%4];"
               : "=r"(r[0]), "=r"(r[1]), "=r"(r[2]), "=r"(r[3]) : "r"(a) : "memory");
}
__device__ __forceinline__ void stsm4(uint32_t a, uint32_t r0, uint32_t r1, uint32_t r2, uint32_t r3) {
  asm volatile("stmatrix.sync.aligned.m8n8.x4.shared.b16 [%0], {%1,%2,%3,%4};"
               ::"r"(a), "r"(r0), "r"(r1), "r"(r2), "r"(r3) : "memory");
}
__device__ __forceinline__ uint32_t lds32(uint32_t a) {
  uint32_t r; asm volatile("ld.shared.u32 %0, [%1];" : "=r"(r) : "r"(a) : "memory"); return r;
}
__device__ __forceinline__ uint32_t lds16(uint32_t a) {
  uint32_t r; asm volatile("{\n.reg .u16 h;\nld.shared.u16 h, [%1];\ncvt.u32.u16 %0, h;\n}\n" : "=r"(r) : "r"(a) : "memory"); return r;
}
__device__ __forceinline__ uint2 lds64(uint32_t a) {
  uint2 r; asm volatile("ld.shared.v2.u32 {%0,%1}, [%2];" : "=r"(r.x), "=r"(r.y) : "r"(a) : "memory"); return r;
}
__device__ __forceinline__ uint4 lds128(uint32_t a) {
  uint4 r;
  asm volatile("ld.shared.v4.u32 {%0,%1,%2,%3}, [%4];" : "=r"(r.x), "=r"(r.y), "=r"(r.z), "=r"(r.w) : "r"(a) : "memory");
  return r;
}
__device__ __forceinline__ void sts32(uint32_t a, uint32_t v) { asm volatile("st.shared.u32 [%0], %1;" ::"r"(a), "r"(v) : "memory"); }
__device__ __forceinline__ void sts16(uint32_t a, uint32_t v) {
  asm volatile("{\n.reg .u16 h;\ncvt.u16.u32 h, %1;\nst.shared.u16 [%0], h;\n}\n" ::"r"(a), "r"(v) : "memory");
}
__device__ __forceinline__ void sts64(uint32_t a, uint32_t x, uint32_t y) {
  asm volatile("st.shared.v2.u32 [%0], {%1,%2};" ::"r"(a), "r"(x), "r"(y) : "memory");
}
__device__ __forceinline__ void sts128(uint32_t a, uint32_t x, uint32_t y, uint32_t z, uint32_t w) {
  asm volatile("st.shared.v4.u32 [%0], {%1,%2,%3,%4};" ::"r"(a), "r"(x), "r"(y), "r"(z), "r"(w) : "memory");
}
__device__ __forceinline__ uint4 ld_x(const uint4* p) {
  uint4 r;
  asm volatile("{\n.reg .b128 t;\nld.relaxed.gpu.global.b128 t, [%4];\nmov.b128 {%0,%1,%2,%3}, t;\n}\n"
               : "=r"(r.x), "=r"(r.y), "=r"(r.z), "=r"(r.w) : "l"(p) : "memory");
  return r;
}
__device__ __forceinline__ uint32_t ld_x32(const uint32_t* p) {
  uint32_t r; asm volatile("ld.relaxed.gpu.global.u32 %0, [%1];" : "=r"(r) : "l"(p) : "memory"); return r;
}
__device__ __forceinline__ void st_x(uint4* p, uint32_t x, uint32_t y, uint32_t z, uint32_t w) {
  asm volatile("{\n.reg .b128 t;\nmov.b128 t, {%1,%2,%3,%4};\nst.relaxed.gpu.global.b128 [%0], t;\n}\n"
               ::"l"(p), "r"(x), "r"(y), "r"(z), "r"(w) : "memory");
}
__device__ __forceinline__ void st_x32(uint32_t* p, uint32_t x) {
  asm volatile("st.relaxed.gpu.global.u32 [%0], %1;" ::"l"(p), "r"(x) : "memory");
}
__device__ __forceinline__ uint32_t nz(uint32_t w) { return max(w, 1u); }
__device__ __forceinline__ uint32_t fu(float x) { return __float_as_uint(x); }
__device__ __forceinline__ float uf(uint32_t x) { return __uint_as_float(x); }

__device__ __forceinline__ void wgmma_ss_n96(float (&d)[48], uint64_t da, uint64_t db, int sc) {
  asm volatile("{\n.reg .pred p;\nsetp.ne.b32 p, %50, 0;\n"
      "wgmma.mma_async.sync.aligned.m64n96k16.f32.bf16.bf16 "
      "{%0,%1,%2,%3,%4,%5,%6,%7,%8,%9,%10,%11,%12,%13,%14,%15,%16,%17,%18,%19,%20,%21,%22,%23,%24,%25,%26,%27,%28,%29,%30,%31,%32,%33,%34,%35,%36,%37,%38,%39,%40,%41,%42,%43,%44,%45,%46,%47}, "
      "%48, %49, p, 1, 1, 0, 1;\n}\n"
      : "+f"(d[0]), "+f"(d[1]), "+f"(d[2]), "+f"(d[3]), "+f"(d[4]), "+f"(d[5]), "+f"(d[6]), "+f"(d[7]),
        "+f"(d[8]), "+f"(d[9]), "+f"(d[10]), "+f"(d[11]), "+f"(d[12]), "+f"(d[13]), "+f"(d[14]), "+f"(d[15]),
        "+f"(d[16]), "+f"(d[17]), "+f"(d[18]), "+f"(d[19]), "+f"(d[20]), "+f"(d[21]), "+f"(d[22]), "+f"(d[23]),
        "+f"(d[24]), "+f"(d[25]), "+f"(d[26]), "+f"(d[27]), "+f"(d[28]), "+f"(d[29]), "+f"(d[30]), "+f"(d[31]),
        "+f"(d[32]), "+f"(d[33]), "+f"(d[34]), "+f"(d[35]), "+f"(d[36]), "+f"(d[37]), "+f"(d[38]), "+f"(d[39]),
        "+f"(d[40]), "+f"(d[41]), "+f"(d[42]), "+f"(d[43]), "+f"(d[44]), "+f"(d[45]), "+f"(d[46]), "+f"(d[47])
      : "l"(da), "l"(db), "r"(sc));
}

__device__ __forceinline__ void wgmma_ss_n128(float (&d)[64], uint64_t da, uint64_t db, int sc) {
  asm volatile("{\n.reg .pred p;\nsetp.ne.b32 p, %66, 0;\n"
      "wgmma.mma_async.sync.aligned.m64n128k16.f32.bf16.bf16 "
      "{%0,%1,%2,%3,%4,%5,%6,%7,%8,%9,%10,%11,%12,%13,%14,%15,%16,%17,%18,%19,%20,%21,%22,%23,%24,%25,%26,%27,%28,%29,%30,%31,%32,%33,%34,%35,%36,%37,%38,%39,%40,%41,%42,%43,%44,%45,%46,%47,%48,%49,%50,%51,%52,%53,%54,%55,%56,%57,%58,%59,%60,%61,%62,%63}, "
      "%64, %65, p, 1, 1, 0, 1;\n}\n"
      : "+f"(d[0]), "+f"(d[1]), "+f"(d[2]), "+f"(d[3]), "+f"(d[4]), "+f"(d[5]), "+f"(d[6]), "+f"(d[7]),
        "+f"(d[8]), "+f"(d[9]), "+f"(d[10]), "+f"(d[11]), "+f"(d[12]), "+f"(d[13]), "+f"(d[14]), "+f"(d[15]),
        "+f"(d[16]), "+f"(d[17]), "+f"(d[18]), "+f"(d[19]), "+f"(d[20]), "+f"(d[21]), "+f"(d[22]), "+f"(d[23]),
        "+f"(d[24]), "+f"(d[25]), "+f"(d[26]), "+f"(d[27]), "+f"(d[28]), "+f"(d[29]), "+f"(d[30]), "+f"(d[31]),
        "+f"(d[32]), "+f"(d[33]), "+f"(d[34]), "+f"(d[35]), "+f"(d[36]), "+f"(d[37]), "+f"(d[38]), "+f"(d[39]),
        "+f"(d[40]), "+f"(d[41]), "+f"(d[42]), "+f"(d[43]), "+f"(d[44]), "+f"(d[45]), "+f"(d[46]), "+f"(d[47]),
        "+f"(d[48]), "+f"(d[49]), "+f"(d[50]), "+f"(d[51]), "+f"(d[52]), "+f"(d[53]), "+f"(d[54]), "+f"(d[55]),
        "+f"(d[56]), "+f"(d[57]), "+f"(d[58]), "+f"(d[59]), "+f"(d[60]), "+f"(d[61]), "+f"(d[62]), "+f"(d[63])
      : "l"(da), "l"(db), "r"(sc));
}

__device__ __forceinline__ void wgmma_ss_n40(float (&d)[20], uint64_t da, uint64_t db, int sc) {
  asm volatile("{\n.reg .pred p;\nsetp.ne.b32 p, %22, 0;\n"
      "wgmma.mma_async.sync.aligned.m64n40k16.f32.bf16.bf16 "
      "{%0,%1,%2,%3,%4,%5,%6,%7,%8,%9,%10,%11,%12,%13,%14,%15,%16,%17,%18,%19}, "
      "%20, %21, p, 1, 1, 1, 1;\n}\n"
      : "+f"(d[0]), "+f"(d[1]), "+f"(d[2]), "+f"(d[3]), "+f"(d[4]), "+f"(d[5]), "+f"(d[6]), "+f"(d[7]),
        "+f"(d[8]), "+f"(d[9]), "+f"(d[10]), "+f"(d[11]), "+f"(d[12]), "+f"(d[13]), "+f"(d[14]), "+f"(d[15]),
        "+f"(d[16]), "+f"(d[17]), "+f"(d[18]), "+f"(d[19])
      : "l"(da), "l"(db), "r"(sc));
}

__device__ __forceinline__ void wgmma_rs_n8(float (&d)[4], const uint4& a, uint64_t db, int sc) {
  asm volatile("{\n.reg .pred p;\nsetp.ne.b32 p, %9, 0;\n"
      "wgmma.mma_async.sync.aligned.m64n8k16.f32.bf16.bf16 "
      "{%0,%1,%2,%3}, "
      "{%4,%5,%6,%7}, %8, p, 1, 1, 1;\n}\n"
      : "+f"(d[0]), "+f"(d[1]), "+f"(d[2]), "+f"(d[3])
      : "r"(a.x), "r"(a.y), "r"(a.z), "r"(a.w), "l"(db), "r"(sc));
}

__device__ __forceinline__ void wgmma_rs_n16(float (&d)[8], const uint4& a, uint64_t db, int sc) {
  asm volatile("{\n.reg .pred p;\nsetp.ne.b32 p, %13, 0;\n"
      "wgmma.mma_async.sync.aligned.m64n16k16.f32.bf16.bf16 "
      "{%0,%1,%2,%3,%4,%5,%6,%7}, "
      "{%8,%9,%10,%11}, %12, p, 1, 1, 1;\n}\n"
      : "+f"(d[0]), "+f"(d[1]), "+f"(d[2]), "+f"(d[3]), "+f"(d[4]), "+f"(d[5]), "+f"(d[6]), "+f"(d[7])
      : "r"(a.x), "r"(a.y), "r"(a.z), "r"(a.w), "l"(db), "r"(sc));
}

__device__ __forceinline__ void wgmma_rs_n24(float (&d)[12], const uint4& a, uint64_t db, int sc) {
  asm volatile("{\n.reg .pred p;\nsetp.ne.b32 p, %17, 0;\n"
      "wgmma.mma_async.sync.aligned.m64n24k16.f32.bf16.bf16 "
      "{%0,%1,%2,%3,%4,%5,%6,%7,%8,%9,%10,%11}, "
      "{%12,%13,%14,%15}, %16, p, 1, 1, 1;\n}\n"
      : "+f"(d[0]), "+f"(d[1]), "+f"(d[2]), "+f"(d[3]), "+f"(d[4]), "+f"(d[5]), "+f"(d[6]), "+f"(d[7]),
        "+f"(d[8]), "+f"(d[9]), "+f"(d[10]), "+f"(d[11])
      : "r"(a.x), "r"(a.y), "r"(a.z), "r"(a.w), "l"(db), "r"(sc));
}

struct Params {
  const __nv_bfloat16 *logA, *Aim, *Cre, *Cim, *logdt, *Dskip, *x, *wphi, *wo;
  __nv_bfloat16* out;
  uint4* xs;
  long long* ts;
};

__device__ __forceinline__ uint4 tr_row(const uint4 (&v)[8], int i) {
  uint32_t o[4];
#pragma unroll
  for (int m = 0; m < 4; m++) {
    const uint4 &ra = v[2 * m], &rb = v[2 * m + 1];
    const int k = i >> 1;
    const uint32_t xa = k == 0 ? ra.x : k == 1 ? ra.y : k == 2 ? ra.z : ra.w;
    const uint32_t xb = k == 0 ? rb.x : k == 1 ? rb.y : k == 2 ? rb.z : rb.w;
    o[m] = __byte_perm(xa, xb, (i & 1) ? 0x7632 : 0x5410);
  }
  return make_uint4(o[0], o[1], o[2], o[3]);
}

struct cpx { float r, i; };
__device__ __forceinline__ cpx csq(cpx a) { return {a.r * a.r - a.i * a.i, 2.f * (a.r * a.i)}; }
__device__ __forceinline__ cpx polar(float e, float t) {
  const float m = ex2(e);
  return {m * __cosf(t), m * __sinf(t)};
}

struct KgenRaw { uint32_t la, ai, cr, ci, ldt; };
__device__ __forceinline__ KgenRaw kgen_load(const Params& P, int d, int unit, int lane, int on) {
  const int o = d * 64 + unit * 32 + lane;
  KgenRaw r = {0, 0, 0, 0, 0};
  asm volatile("{\n.reg .pred p;\nsetp.ne.b32 p, %10, 0;\n@p ld.global.nc.u32 %0, [%5];\n@p ld.global.nc.u32 %1, [%6];\n"
               "@p ld.global.nc.u32 %2, [%7];\n@p ld.global.nc.u32 %3, [%8];\n@p ld.global.nc.u16 %4, [%9];\n}\n"
               : "+r"(r.la), "+r"(r.ai), "+r"(r.cr), "+r"(r.ci), "+r"(r.ldt)
               : "l"((const uint32_t*)P.logA + o), "l"((const uint32_t*)P.Aim + o), "l"((const uint32_t*)P.Cre + o),
                 "l"((const uint32_t*)P.Cim + o), "l"(P.logdt + d), "r"(on));
  return r;
}
struct hc { __half2 r, i; };
struct cpx2 { cpx a, b; };
__device__ __forceinline__ cpx2 csq2(const cpx2& v) { return {csq(v.a), csq(v.b)}; }
__device__ __forceinline__ hc toh(const cpx2& v) { return {__floats2half2_rn(v.a.r, v.b.r), __floats2half2_rn(v.a.i, v.b.i)}; }
__device__ __forceinline__ hc hmul(const hc& z, const hc& w) {
  return {__hfma2(z.r, w.r, __hneg2(__hmul2(z.i, w.i))), __hfma2(z.r, w.i, __hmul2(z.i, w.r))};
}
__device__ __forceinline__ hc hmulc(const hc& z, const hc& w) {
  return {__hfma2(z.r, w.r, __hmul2(z.i, w.i)), __hfma2(z.i, w.r, __hneg2(__hmul2(z.r, w.i)))};
}
__device__ __forceinline__ uint32_t hu(__half2 v) { return *(const uint32_t*)&v; }
__device__ __forceinline__ __half2 uh(uint32_t v) { return *(const __half2*)&v; }

struct KgenAddr { uint32_t sa[2], ld[5][4]; };
__device__ __forceinline__ KgenAddr kgen_addr(int lane, uint32_t buf) {
  KgenAddr a;
  a.sa[0] = buf + (lane & 7) * 128 + ((((lane >> 3) ^ lane) & 7) << 4);
  a.sa[1] = a.sa[0] ^ 64;
  const int q = lane >> 4;
  const uint32_t b = buf + ((lane >> 3) & 1) * 1024 + q * 128;
  const int e[5] = {lane & 7, 0, 1, 2 + (lane & 1), 4 + (lane & 3)};
#pragma unroll
  for (int i = 0; i < 20; i++) {
    a.ld[i >> 2][i & 3] = b + ((e[i >> 2] ^ q ^ (2 * (i & 3))) << 4);
    asm volatile("" : "+r"(a.ld[i >> 2][i & 3]));
  }
  asm volatile("" : "+r"(a.sa[0]), "+r"(a.sa[1]));
  return a;
}
__device__ __forceinline__ void kgen_unit(const KgenRaw& r, const KgenAddr& ad, uint32_t zero, float (&k)[5][4], float& k2048, float& sc) {
  const float dt = bf_round(expf(bf_lo(r.ldt)));
  const uint32_t ar = pack_bf(ex2(bf_lo(r.la) * 1.4426950408889634f), ex2(bf_hi(r.la) * 1.4426950408889634f));
  const float ca = dt * -1.4426950408889634f, a0 = bf_lo(ar) * ca, a1 = bf_hi(ar) * ca;
  const float f0 = bf_lo(r.ai) * dt, f1 = bf_hi(r.ai) * dt;
  const float r0 = f0 * 20.21267777267071f, r1 = f1 * 20.21267777267071f;
  const uint32_t cm = __vmaxu2(r.cr & 0x7fff7fffu, r.ci & 0x7fff7fffu);
  const uint32_t ex = min(max(__reduce_max_sync(0xffffffffu, max(cm >> 16, cm & 0xffffu)) >> 7, 1u), 253u);
  const float cs = uf((254u - ex) << 23);
  sc = 2.f * dt * uf(ex << 23);
  const cpx2 C = {{bf_lo(r.cr) * cs, bf_lo(r.ci) * -cs}, {bf_hi(r.cr) * cs, bf_hi(r.ci) * -cs}};
  auto put = [&](const hc (&v)[8]) {
    stsm4(ad.sa[0], hu(v[0].r), hu(v[1].r), hu(v[2].r), hu(v[3].r));
    stsm4(ad.sa[0] + 1024, hu(v[0].i), hu(v[1].i), hu(v[2].i), hu(v[3].i));
    stsm4(ad.sa[1], hu(v[4].r), hu(v[5].r), hu(v[6].r), hu(v[7].r));
    stsm4(ad.sa[1] + 1024, hu(v[4].i), hu(v[5].i), hu(v[6].i), hu(v[7].i));
    __syncwarp();
  };
  auto get = [&](uint32_t (&o)[4][4], const uint32_t (&a)[4]) {
#pragma unroll
    for (int i = 0; i < 4; i++) ldsm4(o[i], a[i] + i * 256);
  };
  auto at = [](const uint32_t (&o)[4][4], int s) { return hc{uh(o[s >> 1][2 * (s & 1)]), uh(o[s >> 1][2 * (s & 1) + 1])}; };
  uint32_t A[8][4];
  auto tile = [&](int j, const uint32_t (&B)[4][4]) {
    k[j][0] = k[j][1] = k[j][2] = k[j][3] = 0.f;
#pragma unroll
    for (int s = 0; s < 8; s++) mma_h(k[j], A[s], B[s >> 1][2 * (s & 1)], B[s >> 1][2 * (s & 1) + 1]);
  };
  const cpx2 w1 = {polar(a0, f0), polar(a1, f1)};
  const cpx2 w127 = {polar(a0 * 127.f, (r0 - rintf(r0)) * 6.283185307179586f), polar(a1 * 127.f, (r1 - rintf(r1)) * 6.283185307179586f)};
  const cpx2 w2 = csq2(w1), w4 = csq2(w2);
  uint32_t T0[4][4], X[4][4], M[3][4][4];
  {
    hc t[8];
    t[0] = {uh(0x3C003C00u), uh(0u)}; t[1] = toh(w1); t[2] = toh(w2); t[4] = toh(w4);
    t[3] = hmul(t[1], t[2]); t[5] = hmul(t[1], t[4]); t[6] = hmul(t[2], t[4]); t[7] = hmul(t[3], t[4]);
    put(t); get(T0, ad.ld[0]);
  }
  const cpx2 w8 = csq2(w4), w16 = csq2(w8), w32 = csq2(w16), w64 = csq2(w32);
  {
    const hc m8 = toh(w8), m16 = toh(w16), m32 = toh(w32);
    hc a[8];
    a[0] = toh(C); a[1] = hmulc(a[0], m8);
    a[2] = hmulc(a[0], m16); a[3] = hmulc(a[1], m16);
#pragma unroll
    for (int i = 0; i < 4; i++) a[4 + i] = hmulc(a[i], m32);
    put(a); get(X, ad.ld[0]);
  }
    const cpx2 w128 = {{w127.a.r * w1.a.r - w127.a.i * w1.a.i, w127.a.r * w1.a.i + w127.a.i * w1.a.r},
                     {w127.b.r * w1.b.r - w127.b.i * w1.b.i, w127.b.r * w1.b.i + w127.b.i * w1.b.r}};
  const cpx2 w256 = csq2(w128), w512 = csq2(w256);
  const hc m128 = toh(w128), m256 = toh(w256), m512 = toh(w512);
  {
    const hc m254 = toh(csq2(w127)), m127 = toh(w127);
    hc m[8];
    m[0] = toh(w64); m[1] = m128; m[2] = m256; m[3] = hmul(m127, m256);
    m[4] = m512; m[5] = hmul(m127, m512); m[6] = hmul(m[4], m254); m[7] = hmul(m[5], m254);
    put(m);
    get(M[0], ad.ld[1]);
#pragma unroll
    for (int s = 0; s < 8; s++) {
      const hc z = at(X, s), y = hmulc(z, at(M[0], s));
      A[s][0] = hu(z.r) + zero; A[s][1] = hu(y.r); A[s][2] = hu(z.i) + zero; A[s][3] = hu(y.i);
    }
#pragma unroll
    for (int i = 0; i < 3; i++) get(M[i], ad.ld[i + 2]);
  }
  tile(0, T0);
  const cpx2 w1024 = csq2(w512), we = csq2(w1024);
  {
    hc t[8];
    t[0] = toh(w1024); t[1] = hmul(t[0], m128);
    t[2] = hmul(t[0], m256); t[3] = hmul(t[1], m256);
#pragma unroll
    for (int i = 0; i < 4; i++) t[4 + i] = hmul(t[i], m512);
    put(t); get(X, ad.ld[0]);
  }
  k2048 = (C.a.r * we.a.r + C.a.i * we.a.i + C.b.r * we.b.r + C.b.i * we.b.i) * sc;
#pragma unroll
  for (int j = 1; j < 5; j++) k[j][0] = k[j][1] = k[j][2] = k[j][3] = 0.f;
#pragma unroll
  for (int s = 0; s < 8; s++) {
#pragma unroll
    for (int j = 0; j < 3; j++) {
      const hc y = hmul(at(T0, s), at(M[j], s));
      mma_h(k[1 + j], A[s], hu(y.r), hu(y.i));
    }
    mma_h(k[4], A[s], X[s >> 1][2 * (s & 1)], X[s >> 1][2 * (s & 1) + 1]);
  }
}

__device__ __forceinline__ void build_tables(uint32_t tb, int lane, float (&k)[5][4], float k2048) {
  const int g = lane >> 2, c = lane & 3;
  const uint32_t kc = tb + T_KC + 16;
  {
    const uint32_t a0 = kc + 16 * g + 4 * c, a2 = kc + 2 * (256 + 4 * g + c);
    const uint32_t a3 = kc + 2 * (384 + 2 * g + 64 * (c & 1) + (c >> 1)), a4 = kc + 2 * (512 + g + 32 * c);
#pragma unroll
    for (int r = 0; r < 2; r++) {
      sts32(a0 + 128 * r, pack_bf(k[0][2 * r], k[0][2 * r + 1]));
      sts32(a0 + 128 * r + 256, pack_bf(k[1][2 * r], k[1][2 * r + 1]));
      const uint32_t w2 = pack_bf(k[2][2 * r], k[2][2 * r + 1]);
      const uint32_t w3 = pack_bf(k[3][2 * r], k[3][2 * r + 1]);
      const uint32_t w4 = pack_bf(k[4][2 * r], k[4][2 * r + 1]);
      sts16(a2 + 64 * r, w2); sts16(a2 + 64 * r + 128, w2 >> 16);
      sts16(a3 + 32 * r, w3); sts16(a3 + 32 * r + 64, w3 >> 16);
      sts16(a4 + 16 * r, w4); sts16(a4 + 16 * r + 32, w4 >> 16);
    }
  }
  if (lane == 0) { sts16(kc + 2 * 640, pack_bf(k2048, 0.f)); sts32(kc - 4, 0); }
  __syncwarp();
  const uint32_t td = tb + T_D + 32;
#pragma unroll
  for (int hf = 0; hf < 2; hf++) {
    const uint2 v = lds64(kc + 256 * hf + 8 * lane);
    const uint32_t pv = lds32(kc + 256 * hf + 8 * lane - 4);
    sts128(td + 512 * hf + 16 * lane, __byte_perm(v.x, pv, 0x7610), __byte_perm(v.x, v.x, 0x1032), __byte_perm(v.y, v.x, 0x7610),
           __byte_perm(v.y, v.y, 0x1032));
  }
#pragma unroll
  for (int hf = 0; hf < 2; hf++) {
    const uint32_t v = lds32(kc + 512 + 128 * hf + 4 * lane), nx = lds32(kc + 516 + 128 * hf + 4 * lane);
    uint32_t w0 = __byte_perm(v, v, 0x1010);
    const uint32_t w1 = w0;
    if (hf == 0) { const uint32_t pv = lds32(kc + 508); if (lane == 0) w0 = __byte_perm(v, pv, 0x7610); }
    sts128(td + 1024 + 512 * hf + 16 * lane, w0, w1, __byte_perm(v, v, 0x1032), __byte_perm(nx, v, 0x7610));
  }
  {
    const uint32_t kk = lds16(kc + 2 * 384);
    const uint32_t w = lane < 3 ? (kk | (kk << 16)) : (lane == 3 ? (kk << 16) : 0u);
    if (lane < 24) sts32(td + 4 * (lane < 16 ? 512 + lane : lane - 24), w);
    const uint32_t lo_ = lds16(kc + 2 * 511), le_ = lds16(kc + 2 * 512);
    const uint32_t ja = tb + T_5 + (lane < 16 ? 4 * lane : 256 + 4 * lane);
    sts32(ja, lane == 16 ? (le_ << 16) : 0u);
    sts32(ja + 384, lane == 16 ? (lo_ << 16) : 0u);
    sts32(tb + (lane < 16 ? T_7 : T_9 - 64) + 4 * lane, 0u);
  }
#pragma unroll
  for (int s = 0; s < 2; s++) {
    const uint32_t b = kc + 2 * (s ? 512 : 384) + 8 * lane;
    const uint2 v = lds64(b);
    uint32_t em = lds16(b - 2), e0 = v.x;
    const uint32_t e4 = lds16(b + 8);
    if (lane == 0) { em = 0; e0 = 0; }
    sts64(tb + (s ? T_7 : T_3) + 64 + 8 * lane, __byte_perm(v.x, em, 0x5432), __byte_perm(v.y, v.x, 0x7632));
    sts64(tb + (s ? T_9 : T_5) + 64 + 8 * lane, __byte_perm(v.y, e0, 0x5410), __byte_perm(e4, v.y, 0x5410));
  }
  __syncwarp();
}

__device__ __forceinline__ uint32_t box2w(int lo, int n, int o) {
  return ((unsigned)(o - lo) < (unsigned)n ? 0x3F80u : 0u) | ((unsigned)(o + 1 - lo) < (unsigned)n ? 0x3F800000u : 0u);
}

__device__ __forceinline__ void conv_channel(uint32_t ub, uint32_t tb, int lane, uint4* ydst) {
  const int g = lane >> 2, c = lane & 3, x = g - 2 * c;
  const int mi = lane >> 3;
  const uint32_t qa = ub + U_PAD + 16 * (lane & 7) + ((mi == 0 || mi == 3) ? U_ODD : 0) - (mi == 0 ? 16 : 0);
  const uint32_t hb = ub + U_PAD + (mi & 1) * U_ODD + 16 * ((lane >> 4) + (lane & 7)) - 16;
  const uint32_t kv = lds16(tb + T_KC + 16 + 2 * 512);
  const int oh = c < 2 ? 8 + 2 * c : 2 * c - 8, og = c < 3 ? 2 * c : -10;
  uint32_t bx[4] = {box2w(g - 4, 9, 2 * c), box2w(g - 3, 7, 2 * c), box2w(g - 4, 9, oh), box2w(g - 3, 7, oh)};
  uint32_t by[4] = {box2w(g - 10, 5, 2 * c - 8), box2w(g - 5, 3, 2 * c - 8), box2w(g - 10, 5, og), box2w(g - 5, 3, og)};
  uint32_t lb0 = ((unsigned)(x + 5) < 2u ? kv : 0u) | ((unsigned)(x + 4) < 2u ? kv << 16 : 0u);
  uint32_t lb1 = ((unsigned)(x - 3) < 2u ? kv : 0u) | ((unsigned)(x - 4) < 2u ? kv << 16 : 0u);
  const int q0 = g - 1, q1 = c < 3 ? g : g - 2;
  uint32_t y0a = ub + U_PAD + (q0 & 1) * U_ODD + 16 * (q0 >> 1) + 4 * c;
  uint32_t y1a = ub + U_PAD + (q1 & 1) * U_ODD + 16 * (q1 >> 1) + 4 * c;
#pragma unroll
  for (int i = 0; i < 4; i++) asm volatile("" : "+r"(bx[i]), "+r"(by[i]));
  asm volatile("" : "+r"(lb0), "+r"(lb1), "+r"(y0a), "+r"(y1a));
  mbar_wait(BAR(MB_UFULL));
  mbar_spin(BAR(MB_EMPTY + 15));
  TS(36);
  float acc[16][4];
  {
    uint32_t z09[8], z07[8], zm9[8], zm7[8];
#pragma unroll
    for (int i = 0; i < 8; i++) {
      uint32_t h[4];
      ldsm4(h, hb + 128 * i);
      float y0, y1, y2, y3, w0, w1, w2, w3;
      mma0(y0, y1, y2, y3, bx[0], bx[1], bx[2], bx[3], h[2], c < 2 ? h[3] : h[1]);
      mma0(w0, w1, w2, w3, bx[0], bx[1], bx[2], bx[3], h[1], c < 2 ? h[2] : h[0]);
      z09[i] = pack_bf(y0, y1); z07[i] = pack_bf(y2, y3);
      zm9[i] = pack_bf(w0, w1); zm7[i] = pack_bf(w2, w3);
    }
  uint32_t f3[3][4][4];
  {
    const uint32_t fa = tb + T_7 + 4 * (16 + x);
#pragma unroll
    for (int tt = 0; tt < 3; tt++)
#pragma unroll
      for (int D = 0; D < 4; D++) {
        const uint32_t a = fa + (tt == 0 ? 316 : (tt == 1 ? 320 : 0)) + 64 * D;
        f3[tt][D][0] = lds32(a); f3[tt][D][1] = lds32(a + 32); f3[tt][D][2] = lds32(a - 32); f3[tt][D][3] = lds32(a);
      }
  }
    SPLIT();
    nb_sync(NB_GATE, 256);
    SPLIT();
    float a[4][2][4];
#pragma unroll
    for (int kap = 0; kap < 4; kap++)
#pragma unroll
      for (int sg = 0; sg < 2; sg++)
#pragma unroll
        for (int bk = 3; bk >= kap; bk--) {
          const uint32_t(&q0_)[4] = f3[sg ? 2 : 0][bk - kap];
          const uint32_t(&q1_)[4] = f3[sg ? 2 : 1][bk - kap];
          float(&a0)[4] = a[bk][0];
          float(&a1)[4] = a[bk][1];
          if (sg == 0 && kap == 0) {
            mma0(a0[0], a0[1], a0[2], a0[3], q0_[0], q0_[1], q0_[2], q0_[3], z09[0], z09[1]);
            mma0(a1[0], a1[1], a1[2], a1[3], q1_[0], q1_[1], q1_[2], q1_[3], zm9[0], zm9[1]);
          } else {
            mma(a0[0], a0[1], a0[2], a0[3], q0_[0], q0_[1], q0_[2], q0_[3], sg ? zm7[2 * kap] : z09[2 * kap], sg ? zm7[2 * kap + 1] : z09[2 * kap + 1]);
            mma(a1[0], a1[1], a1[2], a1[3], q1_[0], q1_[1], q1_[2], q1_[3], sg ? z07[2 * kap] : zm9[2 * kap], sg ? z07[2 * kap + 1] : zm9[2 * kap + 1]);
          }
        }
    SPLIT();
#pragma unroll
    for (int i = 0; i < 8; i++) {
      uint32_t h[4];
      ldsm4(h, qa + 128 * i);
      const float ci[4] = {a[i >> 1][0][2 * (i & 1)], a[i >> 1][0][2 * (i & 1) + 1], a[i >> 1][1][2 * (i & 1)], a[i >> 1][1][2 * (i & 1) + 1]};
      mmac(acc[8 + i], h[0], h[1], h[2], h[3], lb0, lb1, ci);
    }
  }
  TS(44);
  {
    uint2 a5[10], a3[10];
    const uint32_t aa = tb + T_5 + 4 * (8 + 2 * g - 2 * c);
#pragma unroll
    for (int m = 0; m < 10; m++) { a5[m] = lds64(aa + 32 * m); a3[m] = lds64(aa + 384 + 32 * m); }
    uint32_t x5[12][2], x3[12][2];
    auto ygen = [&](int kap) {
#pragma unroll
      for (int hh = 0; hh < 2; hh++) {
        float y0, y1, y2, y3;
        mma0(y0, y1, y2, y3, by[0], by[1], by[2], by[3], lds32(y0a + 128 * kap + 64 * hh), lds32(y1a + 128 * kap + 64 * hh));
        x5[kap][hh] = pack_bf(y0, y1);
        x3[kap][hh] = pack_bf(y2, y3);
      }
    };
    ygen(11); ygen(10); ygen(9); ygen(8);
#pragma unroll
    for (int kap = 11; kap >= 0; kap--) {
      if (kap >= 4) ygen(kap - 4);
#pragma unroll
      for (int sg = 0; sg < 2; sg++)
#pragma unroll
        for (int i = 4; i >= 0; i--) {
          const int be = kap + 4 + i;
          if (be <= 15) {
            const uint2 &hi = sg ? a3[2 * i + 1] : a5[2 * i + 1], &lo = sg ? a3[2 * i] : a5[2 * i];
            const uint32_t b0 = sg ? x3[kap][0] : x5[kap][0], b1 = sg ? x3[kap][1] : x5[kap][1];
            if (be < 8 && i == 0 && sg == 0) mma0(acc[be][0], acc[be][1], acc[be][2], acc[be][3], hi.x, hi.y, lo.x, lo.y, b0, b1);
            else mma(acc[be][0], acc[be][1], acc[be][2], acc[be][3], hi.x, hi.y, lo.x, lo.y, b0, b1);
          }
        }
    }
  }
  TS(45);
  {
    const uint32_t st = tb + T_ST + lane * 8;
#pragma unroll
    for (int be = 4; be < 12; be++) sts64(st + 256 * be, pack_bf(acc[be][0], acc[be][1]), pack_bf(acc[be][2], acc[be][3]));
    SPLIT();
    uint32_t F[66], qd[8][4];
    const uint32_t fa = tb + T_D + 32 + 4 * x;
#pragma unroll
    for (int i = 0; i < 32; i++) {
      const int s = 120 - (i >> 2) - 8 * (i & 3);
      uint32_t(&q)[4] = qd[i & 7];
      ldsm4(q, qa + 16 * s);
      const int m = 16 * (i & 3) + 2 * (i >> 2);
      F[m] = lds32(fa + 32 * m); F[m + 1] = lds32(fa + 32 * m + 32);
#pragma unroll
      for (int be = 15; be >= 12; be--) {
        const int de = 8 * be - s;
        float(&a)[4] = (be >= 14 && !(i & 1)) ? acc[be - 4] : acc[be];
        if (de >= 0 && be >= 14 && i == 2 * (15 - be)) mma0(a[0], a[1], a[2], a[3], q[0], q[1], q[2], q[3], F[2 * de + 1], F[2 * de]);
        else if (de >= 0) mma(a[0], a[1], a[2], a[3], q[0], q[1], q[2], q[3], F[2 * de + 1], F[2 * de]);
      }
    }
#pragma unroll
    for (int i = 0; i < 8; i++) acc[14 + (i >> 2)][i & 3] += acc[10 + (i >> 2)][i & 3];
    F[64] = lds32(fa + 32 * 64); F[65] = lds32(fa + 32 * 65);
#pragma unroll
    for (int i = 0; i < 6; i++) ldsm4(qd[i], qa + 128 * 11 - 16 * i);
    uint2 sv = lds64(st + 256 * 11);
    float ci[4] = {bf_lo(sv.x), bf_hi(sv.x), bf_lo(sv.y), bf_hi(sv.y)};
    float T[5][4];
#pragma unroll
    for (int i = 0; i < 16; i++) T[i >> 2][i & 3] = acc[12 + (i >> 2)][i & 3];
    nb_sync(NB_YZ, 160);
    TS(46);
    uint32_t held[2];
#pragma unroll
    for (int be = 11; be >= 0; be--) {
      if (be & 1) SPLITN(be);
      const uint32_t qp = qa + 128 * be;
#pragma unroll
      for (int k = 4; k >= 1; k--) mmac(T[k], qd[0][0], qd[0][1], qd[0][2], qd[0][3], F[16 * k + 1], F[16 * k], T[k - 1]);
      if (be >= 4) mmac(T[0], qd[0][0], qd[0][1], qd[0][2], qd[0][3], F[1], F[0], ci);
      else mma0(T[0][0], T[0][1], T[0][2], T[0][3], qd[0][0], qd[0][1], qd[0][2], qd[0][3], F[1], F[0]);
      ldsm4(qd[6], qp - 16 * 6);
      ldsm4(qd[7], qp - 16 * 7);
      if (be > 4) sv = lds64(st + 256 * (be - 1));
#pragma unroll
      for (int i = 1; i < 8; i++) {
#pragma unroll
        for (int k = 3; k >= 0; k--)
          mma(T[k][0], T[k][1], T[k][2], T[k][3], qd[i][0], qd[i][1], qd[i][2], qd[i][3], F[16 * k + 2 * i + 1], F[16 * k + 2 * i]);
        if (i < 7 && be > 0) ldsm4(qd[i - 1], qp - 128 - 16 * (i - 1));
        if (i == 2) {
          const uint32_t w0 = pack_bf(T[4][0], T[4][1]), w1 = pack_bf(T[4][2], T[4][3]);
          if (be & 1) { held[0] = w0; held[1] = w1; }
          else st_x(ydst + (be + 4) * 16, nz(w0), w1, held[0], held[1]);
          if ((be & 3) == 3 && be < 11) nb_arrive(NB_Y + 2 + (be >> 2), 160);
        }
        if (i == 4 && be > 4) { ci[0] = bf_lo(sv.x); ci[1] = bf_hi(sv.x); ci[2] = bf_lo(sv.y); ci[3] = bf_hi(sv.y); }
      }
    }
    if ((fu(T[0][0]) & fu(T[1][0]) & fu(T[2][0]) & fu(T[3][0])) == 0xffffffffu) sts32(st, 0);
    nb_arrive(NB_BDONE, 288);
    nb_arrive(NB_Y + 1, 160);
#pragma unroll
    for (int B = 1; B >= 0; B--)
      st_x(ydst + B * 32, nz(pack_bf(T[2 * B][0], T[2 * B][1])), pack_bf(T[2 * B][2], T[2 * B][3]),
           pack_bf(T[2 * B + 1][0], T[2 * B + 1][1]), pack_bf(T[2 * B + 1][2], T[2 * B + 1][3]));
  }
}

__device__ __forceinline__ void dual_exp(const uint32_t* w, uint32_t* e) {
  const float L = 1.44268798828125f;
  uint32_t mx = bmax2(bmax2(w[0], w[1]), bmax2(w[2], w[3]));
  uint32_t mn = bmin2(bmin2(w[0], w[1]), bmin2(w[2], w[3]));
  mx = bmax2(mx, __shfl_xor_sync(0xffffffffu, mx, 1));
  mn = bmin2(mn, __shfl_xor_sync(0xffffffffu, mn, 1));
  mx = bmax2(mx, __shfl_xor_sync(0xffffffffu, mx, 2));
  mn = bmin2(mn, __shfl_xor_sync(0xffffffffu, mn, 2));
  const float mx0 = bf_lo(mx) * -L, mx1 = bf_hi(mx) * -L, mn0 = bf_lo(mn) * L, mn1 = bf_hi(mn) * L;
#pragma unroll
  for (int i = 0; i < 2; i++) {
    const float a0 = bf_lo(w[2 * i]), a1 = bf_hi(w[2 * i]), b0 = bf_lo(w[2 * i + 1]), b1 = bf_hi(w[2 * i + 1]);
    e[2 * i] = pack_bf(ex2(fmaf(a0, L, mx0)), ex2(fmaf(b0, L, mx0)));
    e[2 * i + 1] = pack_bf(ex2(fmaf(a1, L, mx1)), ex2(fmaf(b1, L, mx1)));
    e[4 + 2 * i] = pack_bf(ex2(fmaf(a0, -L, mn0)), ex2(fmaf(b0, -L, mn0)));
    e[5 + 2 * i] = pack_bf(ex2(fmaf(a1, -L, mn1)), ex2(fmaf(b1, -L, mn1)));
  }
}
__device__ __forceinline__ void normalise(uint32_t* e, const float (&s)[4]) {
  const uint32_t r = pack_bf(rcp(s[0]), rcp(s[2]));
  const __nv_bfloat162 rr = *(const __nv_bfloat162*)&r;
#pragma unroll
  for (int i = 0; i < 4; i++) {
    const __nv_bfloat162 v = __hmul2(*(const __nv_bfloat162*)&e[i], (i & 1) ? __high2bfloat162(rr) : __low2bfloat162(rr));
    e[i] = *(const uint32_t*)&v;
  }
}
__host__ __device__ constexpr uint64_t qdesc(uint32_t addr) { return mkdesc(addr, 128, 256, 0); }

__global__ void __launch_bounds__(NTHREADS, 1)
fused_kernel(const Params P, const __grid_constant__ CUtensorMap mx, const __grid_constant__ CUtensorMap mw,
             const __grid_constant__ CUtensorMap mo, const __grid_constant__ CUtensorMap mu,
             const __grid_constant__ CUtensorMap mout) {
  constexpr uint32_t sb = SB;
  const int tid = threadIdx.x, lane = tid & 31;
  const int warp = __shfl_sync(0xffffffffu, tid >> 5, 0);
  const int b = blockIdx.x, oct = b >> 3, i8 = b & 7;
  const int rt = (((oct & 4) ? ~oct : oct) & 3) * 2 + (i8 >> 2);
  const int hp = (oct >> 2) * 4 + (i8 & 3);

  const int wg = warp >> 2, w = warp & 3;
  const int d = b * 4 + ((tid >> 5) & 3);
  const KgenRaw raw = kgen_load(P, d, (tid >> 7) & 1, lane, (tid + 128) & 256);
  const uint32_t tb = sb + OFF_T + w * T_CH;
  if (warp >= 12) {
    asm volatile("setmaxnreg.dec.sync.aligned.u32 32;");
    if (warp == 12) {
      if (lane == 0) {
#pragma unroll
        for (int i = 0; i < 9; i++) mbar_init(BAR(i), 1);
        asm volatile("fence.mbarrier_init.release.cluster;" ::: "memory");
      }
      __syncwarp();
      if (lane < 9) mbar_expect(BAR(0) + 8 * lane, lane == 0 ? 16384 : 28672);
      __syncwarp();
      nb_arrive(NB_PROD, 384);
#pragma unroll 1
      for (int kb = 0; kb < 8; kb++) {
        if (kb == U_AT) e_tma4d(sb + OFF_STG0, &mu, BAR(MB_URAW), i8 * 64, oct * 2);
        e_tma3d(sb + OFF_W + kb * 12288, &mw, BAR(MB_FULL) + 8 * kb, hp * 32, kb * 64, 0);
        if (kb < 5) e_tma2d(sb + OFF_X + (kb < 2 ? kb + 3 : kb - 2) * 16384, &mx, BAR(MB_FULL) + 8 * kb, kb * 64, rt * 256);
      }
      if (smem_u32(smem_raw) != SB) __trap();
      if (lane == 0) TS1(54);
      nb_sync(NB_GATE + 1, 64);
      e_prefetch(P.x + (size_t)(rt * 256 + 128 + hp * 8) * 512, 8192);
      uint32_t slot = sb + OFF_X + 3 * 16384;
#pragma unroll 1
      for (int n = 0; n < 11; n++) {
        mbar_spin(BAR(MB_EMPTY) + 8 * n);
        const int m = n + 5;
        e_tma2d(slot, &mx, BAR(MB_FULL) + 8 * m, (m & 7) * 64, rt * 256 + (m >> 3) * 128);
        slot = slot == sb + OFF_X + 4 * 16384 ? sb + OFF_X : slot + 16384;
        if (n == 7) {
          e_prefetch(P.wo + (size_t)b * 2048, 4096);
          asm volatile("prefetch.tensormap [%0];" ::"l"(&mo) : "memory");
          asm volatile("prefetch.tensormap [%0];" ::"l"(&mout) : "memory");
        }
      }
#pragma unroll 1
      for (int i = 0; i < 8; i++) {
        mbar_wait(BAR(MB_EMPTY + 10) + 8 * ((0x54332222u >> (4 * i)) & 7));
        const int w0 = (0x54736210u >> (4 * i)) & 7;
        e_tma3d(sb + OFF_W + w0 * 16384, &mo, BAR(MB_WO), 0, w0 * 64, (hp & 3) * 2);
      }
    } else {
      if (warp == 13) {
        if (lane == 0) {
#pragma unroll
          for (int i = 9; i < 40; i++) mbar_init(BAR(i), i < MB_EMPTY ? 1 : 4);
          asm volatile("fence.mbarrier_init.release.cluster;" ::: "memory");
        }
        __syncwarp();
        if (lane < 14 && lane != 9) mbar_expect(BAR(MB_FULL + 8) + 8 * lane, lane == 8 ? 131072 : (lane == 10 ? 8192 : (lane == 13 ? 24576 : 16384)));
        nb_arrive(NB_GATE + 1, 64);
      } else if (warp == 14) {
        asm volatile("prefetch.tensormap [%0];" ::"l"(&mw) : "memory");
        asm volatile("prefetch.tensormap [%0];" ::"l"(&mx) : "memory");
        asm volatile("prefetch.tensormap [%0];" ::"l"(&mu) : "memory");
        e_prefetch(P.x + (size_t)(rt * 256 + hp * 8) * 512, 8192);
      }
      nb_sync(NB_PROD, 384);
      if (warp == 15) {
        const uint4 v0 = __ldg((const uint4*)P.wphi + hp * 64 + lane), v1 = __ldg((const uint4*)P.wphi + hp * 64 + 32 + lane);
        sts128(sb + OFF_PHI + (lane & 1) * 256 + (lane >> 1) * 16, v0.x, v0.y, v0.z, v0.w);
        sts128(sb + OFF_PHI + 512 + (lane & 1) * 256 + (lane >> 1) * 16, v1.x, v1.y, v1.z, v1.w);
        const uint32_t one = (((lane >> 3) ^ (lane >> 4)) & 1) ? 0u : ((lane & 1) ? 0x3F800000u : 0x3F80u);
        const int q = (lane >> 1) & 3;
        sts128(sb + OFF_EYE + lane * 16, q == 0 ? one : 0u, q == 1 ? one : 0u, q == 2 ? one : 0u, q == 3 ? one : 0u);
        sts64(sb + OFF_ONE + lane * 8, 0x3F803F80u, 0x3F803F80u);
        asm volatile("fence.proxy.async.shared::cta;" ::: "memory");
        nb_arrive(NB_KREAD, 160);
      }
      uint32_t* cnt = (uint32_t*)(P.xs + X_CNT) + (warp == 13 ? i8 : (warp == 14 ? 8 + rt : 16 + oct)) * 32;
      const unsigned target = (ld_x32(cnt) & ~15u) + 16;
      if (warp != 14) {
        if (warp == 15) mbar_wait(BAR(MB_EMPTY + ZERO_STEP));
        uint4* pz = P.xs + (warp == 13 ? X_PART + (hp * 8 + rt) * 144 : X_Y + b * 1024) + lane;
#pragma unroll 1
        for (int i = (warp == 13 ? 144 : 1024) - lane; i > 0; i -= 32, pz += 32) st_x(pz, 0, 0, 0, 0);
      }
      if (warp == 15) __syncwarp();
      else nb_sync(warp == 13 ? NB_INIT : NB_ODONE, warp == 13 ? 160 : 288);
      if (lane == 0) asm volatile("red.release.gpu.global.add.u32 [%0], %1;" ::"l"(cnt), "r"(warp == 15 ? 2 : 1) : "memory");
      if (lane == 0) TS1(warp == 13 ? 50 : (warp == 14 ? 57 : 53));
      __syncwarp();
      if (warp == 14) nb_arrive(NB_GATE + 1, 160);
      asm volatile("fence.proxy.async.shared::cta;" ::: "memory");
      if (warp == 13) cnt += ((lane & 1 ? b >> 4 : i8 ^ (lane & 4)) - i8) * 32;
#pragma unroll 1
      for (int i = 0; i < SPIN_MAX; i++) {
        unsigned v;
        asm volatile("ld.acquire.gpu.global.u32 %0, [%1];" : "=r"(v) : "l"(cnt) : "memory");
        if (__all_sync(0xffffffffu, (int)(v - target) >= 0)) break;
      }
      if (lane == 0) TS1(warp == 13 ? 51 : (warp == 14 ? 58 : 55));
      if (warp == 15) { nb_arrive(NB_YZ, 160); return; }
      asm volatile("fence.proxy.async.global;" ::: "memory");
      if (warp == 13) {
        mbar_wait(BAR(MB_EMPTY + 11));
        e_expect(BAR(MB_UFULL), 4 * U_CH);
        e_bulk(sb + OFF_U, P.xs + X_UT + b * (U_CH / 4), 4 * U_CH, BAR(MB_UFULL));
      } else {
        const uint4* src = P.xs + X_O + (rt * 4 + (hp >> 2)) * 4096;
        e_bulk(sb + OFF_X + 32768 + 57344, src + 3584, 8192, BAR(MB_O));
        e_bulk(sb + OFF_X + 32768, src, 16384, BAR(MB_O + 1));
        e_bulk(sb + OFF_X + 49152, src + 1024, 16384, BAR(MB_O + 2));
        e_bulk(sb + OFF_STG0, src + 3200, 6144, BAR(MB_O + 3));
        nb_sync(NB_BDONE, 288);
        asm volatile("fence.proxy.async.shared::cta;" ::: "memory");
        e_bulk(sb + OFF_U, src + 2048, 18432, BAR(MB_O + 3));
      }
    }
    return;
  }

  asm volatile("setmaxnreg.inc.sync.aligned.u32 160;");
  const int t = tid & 127;
  const int g = lane >> 2, c = lane & 3;
  const uint32_t kp = ((tb + 127) & ~127u) + (wg & 1) * 2048;
  const KgenAddr kad = kgen_addr(lane, kp);
  if (wg) nb_sync(NB_PROD, 384);
  SPLIT();
  float k[5][4], k2048, ksc;
  if (wg) {
    kgen_unit(raw, kad, blockIdx.y, k, k2048, ksc);
    TS(40 + wg);
    if ((fu(k[0][0]) & fu(k[1][0]) & fu(k[2][0]) & fu(k[3][0]) & fu(k[4][0])) == 0xffffffffu) sts32(kp, 0);
  }
  if (wg) nb_arrive(0, 384);
  if (wg) {
    if (wg == 1) {
      uint32_t h[10];
#pragma unroll
      for (int j = 0; j < 10; j++) h[j] = hu(__floats2half2_rn(k[j >> 1][2 * (j & 1)], k[j >> 1][2 * (j & 1) + 1]));
      sts128(kp + lane * 16, h[0], h[1], h[2], h[3]);
      sts128(kp + 512 + lane * 16, h[4], h[5], h[6], h[7]);
      sts128(kp + 1024 + lane * 16, h[8], h[9], fu(k2048), fu(ksc));
      nb_arrive(NB_PREP, 256);
    }
  } else {
    nb_sync(NB_KREAD, 160);
  }
  if (wg == 1) {
    mbar_wait(BAR(MB_URAW));
    TS(48);
    uint4* dst = P.xs + X_UT + (i8 * 64 + g) * (U_CH / 16) + (w & 1) * (U_ODD / 16) + U_PAD / 16 + oct * 8 + (w >> 1) * 4 + c;
    const int ln = ((lane >> 1) & 3) + 4 * (lane & 1);
    uint32_t r[8][4];
#pragma unroll
    for (int i = 0; i < 8; i++) ldsm4t(r[i], sb + OFF_STG0 + w * 4096 + ((lane >> 3) * 8 + ln) * 128 + ((i ^ ln) << 4));
#pragma unroll
    for (int i = 0; i < 8; i++) dst[i * (U_CH / 2)] = make_uint4(r[i][0], r[i][1], r[i][2], r[i][3]);
    nb_arrive(NB_INIT, 160);
    if (lane == 0) mbar_arrive(BAR(MB_AUX));
  }
  {
    if (wg == 2) {
#pragma unroll
      for (int j = 0; j < 5; j++) { k[j][0] *= ksc; k[j][1] *= ksc; k[j][2] *= ksc; k[j][3] *= ksc; }
      const unsigned short dsk = __ldg((const unsigned short*)P.Dskip + d);
      nb_sync(NB_PREP, 256);
      {
        const uint32_t src = kp + 2048 + lane * 16;
        const uint4 v0 = lds128(src), v1 = lds128(src + 512), v2 = lds128(src + 1024);
        const uint32_t h[10] = {v0.x, v0.y, v0.z, v0.w, v1.x, v1.y, v1.z, v1.w, v2.x, v2.y};
#pragma unroll
        for (int j = 0; j < 10; j++) {
          const float2 f = __half22float2(*(const __half2*)&h[j]);
          k[j >> 1][2 * (j & 1)] = fmaf(f.x, uf(v2.w), k[j >> 1][2 * (j & 1)]);
          k[j >> 1][2 * (j & 1) + 1] = fmaf(f.y, uf(v2.w), k[j >> 1][2 * (j & 1) + 1]);
        }
        k2048 += uf(v2.z);
      }
#pragma unroll
      for (int o2 = 16; o2; o2 >>= 1) k2048 += __shfl_xor_sync(0xffffffffu, k2048, o2);
      if (lane == 0) k[0][0] += bf_lo(dsk);
      __syncwarp();
      TS(34);
      build_tables(tb, lane, k, k2048);
      TS(35);
      uint4* const g_y = P.xs + X_Y;
      conv_channel(sb + OFF_U + w * U_CH, tb, lane, g_y + (size_t)d * 256 + lane);
      nb_arrive(NB_Y, 160);
      TS(37);
      if (w == 0) TSDUMP(32);
      return;
    }
    if (wg == 1) {
      mbar_wait(BAR(MB_EMPTY + 4));
      mbar_spin(BAR(MB_EMPTY + 6));
    }
    TS(wg * 16 + 1);
  }

  float acc[2][48];
  {
    uint32_t fb = BAR(MB_FULL) + 64 * wg;
    uint32_t da = (uint32_t)mkdesc(sb + OFF_X, 16, 0, 0) + (wg ? 1024 : 3072), db = (uint32_t)mkdesc(sb + OFF_W, 4096, 0, 0);
    constexpr uint64_t ha = mkdesc(0, 0, 1024, 1), hb = mkdesc(0, 0, 512, 2);
    mbar_spin(fb);
    if (wg == 0) nb_sync(0, 384);
    TS(wg * 16 + 2);
#pragma unroll 1
    for (int kb = 0; kb < 8; kb++) {
      WG_FENCE();
#pragma unroll
      for (int k = 0; k < 4; k++) {
        wgmma_ss_n96(acc[0], ha | (da + 2 * k), hb | (db + 64 * k), k ? 1 : kb);
        wgmma_ss_n96(acc[1], ha | (da + 2 * k + 512), hb | (db + 64 * k), k ? 1 : kb);
      }
      WG_COMMIT();
      if (kb < 7) mbar_spin(fb + 8);
      WG_WAIT(1);
      if (kb > 0) e_arrive(fb + 8 * (MB_EMPTY - MB_FULL - 1));
      fb += 8; db += 768;
      da = da == (uint32_t)mkdesc(sb + OFF_X + 65536, 16, 0, 0) ? da - 4096 : da + 1024;
    }
    WG_WAIT(0);
    e_arrive(fb + 8 * (MB_EMPTY - MB_FULL - 1));
    SPLIT();
  }
  TS(wg * 16 + 3);

  constexpr uint32_t stg0 = sb + OFF_STG0, stg1 = sb + OFF_X + 32768;
  uint4* const g_part = P.xs + X_PART;
  uint4* const g_o = P.xs + X_O;
  constexpr uint32_t kvs = stg0;
  auto pack8 = [](const float* a) { return make_uint4(pack_bf(a[0], a[1]), pack_bf(a[2], a[3]), pack_bf(a[4], a[5]), pack_bf(a[6], a[7])); };
  auto stage_k = [&](auto nt, const uint4* af, const uint4* vp, uint32_t sl, uint32_t free_bar) {
    constexpr int NU = 2 * decltype(nt)::value;
    float p[NU][8], rs[2 * NU][4];
    uint32_t ek[8 * NU];
    WG_FENCE();
#pragma unroll
    for (int u = 0; u < NU; u++) wgmma_rs_n16(p[u], af[u], qdesc(sb + OFF_PHI + (u & 1) * 512), 0);
    WG_COMMIT();
    WG_WAIT(0);
#pragma unroll
    for (int u = 0; u < NU; u++) {
      const uint32_t pw[4] = {pack_bf(p[u][0], p[u][2]), pack_bf(p[u][1], p[u][3]), pack_bf(p[u][4], p[u][6]), pack_bf(p[u][5], p[u][7])};
      dual_exp(pw, ek + 8 * u);
    }
    TS(wg * 16 + 12);
    mbar_spin(free_bar);
    WG_FENCE();
#pragma unroll
    for (int i = 0; i < 2 * NU; i++) wgmma_rs_n8(rs[i], make_uint4(ek[4 * i], ek[4 * i + 1], ek[4 * i + 2], ek[4 * i + 3]), qdesc(sb + OFF_ONE), 0);
    WG_COMMIT();
#pragma unroll
    for (int i = 0; i < NU; i++) stsm4(sl + (i >> 1) * 4 * SLAB + 2048 + (i & 1) * 512, vp[i].x, vp[i].y, vp[i].z, vp[i].w);
    if (NU == 4 || lane < 16) sts128(sl + (lane >> 4) * (4 * SLAB - 256) + 3072, 0x3F803F80u, 0x3F803F80u, 0x3F803F80u, 0x3F803F80u);
    WG_WAIT(0);
#pragma unroll
    for (int i = 0; i < 2 * NU; i++) {
      normalise(ek + 4 * i, rs[i]);
      stsm4(sl + (i >> 2) * 4 * SLAB + (i & 3) * 512, ek[4 * i], ek[4 * i + 1], ek[4 * i + 2], ek[4 * i + 3]);
    }
    asm volatile("fence.proxy.async.shared::cta;" ::: "memory");
  };
  auto contract = [&](float (&kc)[20], uint32_t stg, int acc_in) {
    WG_FENCE();
#pragma unroll
    for (int s = 0; s < 8; s++) wgmma_ss_n40(kc, qdesc(stg + s * SLAB), qdesc(stg + s * SLAB + 2048), s ? 1 : acc_in);
    WG_COMMIT();
    WG_WAIT(0);
  };
  uint32_t eq[32];
  {
    uint4 af[4], aq[4], vp[4];
    float kc[20];
#pragma unroll
    for (int u = 0; u < 4; u++) { af[u] = pack8(acc[u >> 1] + 16 + 8 * (u & 1)); vp[u] = pack8(acc[u >> 1] + 32 + 8 * (u & 1)); }
    const uint32_t hand = stg1 + 16384 + 8192 + w * 2048 + lane * 16;
    if (wg) {
      sts128(hand, af[2].x, af[2].y, af[2].z, af[2].w); sts128(hand + 512, af[3].x, af[3].y, af[3].z, af[3].w);
      sts128(hand + 1024, vp[2].x, vp[2].y, vp[2].z, vp[2].w); sts128(hand + 1536, vp[3].x, vp[3].y, vp[3].z, vp[3].w);
      nb_arrive(NB_HAND, 256);
    }
#pragma unroll
    for (int u = 0; u < 4; u++) aq[u] = pack8(acc[u >> 1] + 8 * (u & 1));
    if (wg == 0) {
      stage_k(std::integral_constant<int, 2>(), af, vp, stg0 + w * SLAB + lane * 16, BAR(MB_AUX));
      TS(13);
      nb_sync(NB_WG0, 128);
      contract(kc, stg0, 0);
      mbar_wait(BAR(MB_UFULL));
      TS(15);
      nb_sync(NB_HAND, 256);
      af[0] = lds128(hand); af[1] = lds128(hand + 512); vp[0] = lds128(hand + 1024); vp[1] = lds128(hand + 1536);
      nb_sync(NB_WG0, 128);
    }
    stage_k(std::integral_constant<int, 1>(), af, vp, stg1 + (wg ? w : 4 + w) * SLAB + lane * 16, BAR(MB_EMPTY + 15));
    TS(wg * 16 + 14);
    float p[4][8];
    if (wg) {
      nb_arrive(NB_ST0, 256);
      nb_arrive(NB_GATE, 256);
    } else {
      uint4* pp = g_part + (size_t)(hp * 8 + rt) * 144 + t;
      uint32_t* pz = (uint32_t*)(pp - t + 128) + w * 16 + c * 8 + g;
      asm volatile("" : "+l"(pp), "+l"(pz));
      nb_sync(NB_ST0, 256);
      contract(kc, stg1, 1);
      TS(6);
      float kv[8];
#pragma unroll
      for (int i = 0; i < 8; i++) kv[i] = w & 2 ? kc[8 + i] : kc[i];
      st_x(pp, nz(pack_bf(kv[0], kv[1])), pack_bf(kv[2], kv[3]), pack_bf(kv[4], kv[5]), pack_bf(kv[6], kv[7]));
      if (c < 2) st_x32(pz, nz(fu(c ? kc[18] : kc[16])));
      TS(5);
    }
    SPLIT();
    WG_FENCE();
#pragma unroll
    for (int u = 0; u < 4; u++) wgmma_rs_n16(p[u], aq[u], qdesc(sb + OFF_PHI + (u & 1) * 512), 0);
    WG_COMMIT();
    WG_WAIT(0);
#pragma unroll
    for (int u = 0; u < 4; u++) {
      const uint32_t pw[4] = {pack_bf(p[u][0], p[u][2]), pack_bf(p[u][1], p[u][3]), pack_bf(p[u][4], p[u][6]), pack_bf(p[u][5], p[u][7])};
      dual_exp(pw, eq + 8 * u);
    }
    SPLIT();
  }
  TS(wg * 16 + 4);
  if (wg == 1) {
    mbar_wait(BAR(MB_UFULL));
    const uint4* ps = g_part + (size_t)hp * 8 * 144 + t;
    const uint32_t* zs = (const uint32_t*)(g_part + (size_t)(hp * 8 + (lane >> 4) * 4) * 144 + 128) + w * 16 + (lane & 15);
    uint4 v[8];
    uint32_t zv[4];
#pragma unroll 1
    for (int it = 0; it < SPIN_MAX; it++) {
#pragma unroll
      for (int i = 0; i < 8; i++) v[i] = ld_x(ps + i * 144);
#pragma unroll
      for (int i = 0; i < 4; i++) zv[i] = ld_x32(zs + i * 576);
      uint32_t m = min(min(zv[0], zv[1]), min(zv[2], zv[3]));
#pragma unroll
      for (int i = 0; i < 8; i++) m = min(m, v[i].x);
      if (__all_sync(0xffffffffu, m != 0)) break;
    }
    float s[8];
    WG_FENCE();
#pragma unroll
    for (int r = 0; r < 8; r++) wgmma_rs_n16(s, v[r], qdesc(sb + OFF_EYE), r);
    WG_COMMIT();
    float zsum = (uf(zv[0]) + uf(zv[1])) + (uf(zv[2]) + uf(zv[3]));
    zsum += __shfl_xor_sync(0xffffffffu, zsum, 16);
    const uint32_t z1 = pack_bf(zsum, 1.f);
    if (lane < 16) sts128(kvs + w * 768 + 512 + lane * 16, z1, z1, z1, z1);
    WG_WAIT(0);
    stsm4(kvs + w * 768 + lane * 16, pack_bf(s[0], s[1]), pack_bf(s[2], s[3]), pack_bf(s[4], s[5]), pack_bf(s[6], s[7]));
    asm volatile("fence.proxy.async.shared::cta;" ::: "memory");
    TS(22);
  }
  nb_sync(NB_KV, 256);
  {
    float n[8][12];
    WG_FENCE();
#pragma unroll
    for (int i = 0; i < 8; i++) wgmma_rs_n24(n[i], make_uint4(eq[4 * i], eq[4 * i + 1], eq[4 * i + 2], eq[4 * i + 3]), qdesc(kvs + (i & 3) * 768), 0);
    WG_COMMIT();
    uint32_t* od = (uint32_t*)(g_o + (size_t)((rt * 4 + wg * 2) * 32 + hp * 2) * 128) + w * 64 + lane;
    WG_WAIT(0);
#pragma unroll
    for (int u = 0; u < 4; u++) {
      float(&np)[12] = n[2 * u];
      const float(&nm)[12] = n[2 * u + 1];
      const float q0 = np[9] * rcp(nm[9]), q1 = np[11] * rcp(nm[11]);
      const float r0 = rcp(fmaf(nm[8], q0, fmaf(np[9], 1e-6f, np[8]))), r1 = rcp(fmaf(nm[10], q1, fmaf(np[11], 1e-6f, np[10])));
#pragma unroll
      for (int i = 0; i < 8; i++) np[i] = fmaf(nm[i], (i & 2) ? q1 : q0, np[i]);
      uint32_t* o = od + (u >> 1) * 16384 + (u & 1) * 512;
      o[0] = pack_bf(np[0] * r0, np[1] * r0);
      o[32] = pack_bf(np[2] * r1, np[3] * r1);
      o[256] = pack_bf(np[4] * r0, np[5] * r0);
      o[288] = pack_bf(np[6] * r1, np[7] * r1);
      if (u == 1) SPLIT();
    }
  }
  TS(wg * 16 + 7);
  nb_arrive(NB_ODONE, 288);
  if (wg) {
    const uint4* src = P.xs + X_Y + (oct * 32 + c * 8) * 256 + (2 * w + (g >> 2)) * 32 + i8 * 4 + (g & 3);
    __nv_bfloat16* dst = P.out + (size_t)((2 * w + (g >> 2)) * 256 + i8 * 16 + (g & 3) * 2) * 1024 + 512 + oct * 32 + c * 8;
    nb_sync(NB_GATE + 1, 160);
    nb_sync(NB_Y + w, 160);
    uint4 v[8];
#pragma unroll 1
    for (int it = 0; it < SPIN_MAX; it++) {
      uint32_t m = 0xffffffffu;
#pragma unroll
      for (int i = 0; i < 8; i++) v[i] = ld_x(src + i * 256);
#pragma unroll
      for (int i = 0; i < 8; i++) m = min(m, v[i].x);
      if (__all_sync(0xffffffffu, m != 0)) break;
    }
#pragma unroll
    for (int i = 0; i < 8; i++) *(uint4*)(dst + (size_t)((i >> 2) * 128 + ((i >> 1) & 1) * 8 + (i & 1)) * 1024) = tr_row(v, i);
    TS(31);
    GT(63);
    if (w == 0) TSDUMP(16);
    return;
  }
  mbar_wait(BAR(MB_WO));
  nb_sync(NB_BDONE, 288);
  TS(8);
  mbar_spin(BAR(MB_O));
  TS(9);
  constexpr uint64_t ha = mkdesc(0, 0, 128, 0), hb = mkdesc(0, 0, 1024, 1);
  constexpr uint32_t da0 = (uint32_t)mkdesc(stg1, 1024, 0, 0), db0 = (uint32_t)mkdesc(sb + OFF_W, 8192, 0, 0);
  const uint32_t ot = ((sb + OFF_T + 1023) & ~1023u) + w * 4096;
  auto store_half = [&](const float* oc, int hf) {
#pragma unroll
    for (int i = 0; i < 8; i += 2)
      stsm4(ot + hf * 2048 + (lane & 15) * 128 + (((i + (lane >> 4)) ^ lane) & 7) * 16, pack_bf(oc[4 * i], oc[4 * i + 1]),
            pack_bf(oc[4 * i + 2], oc[4 * i + 3]), pack_bf(oc[4 * i + 4], oc[4 * i + 5]), pack_bf(oc[4 * i + 6], oc[4 * i + 7]));
    asm volatile("fence.proxy.async.shared::cta;" ::: "memory");
    __syncwarp();
    e_store2d(&mout, ot + hf * 2048, (hp & 3) * 128 + hf * 64, (rt * 4 + (hp >> 2)) * 64 + w * 16);
  };
  float oc[64];
#pragma unroll 1
  for (int j = 0; j < 8; j++) {
    const int kb = (j + 7) & 7;
    if ((j & 1) && j < 6) mbar_spin(BAR(MB_O + 1) + 4 * (j - 1));
    WG_FENCE();
#pragma unroll
    for (int k = 0; k < 4; k++) wgmma_ss_n128(oc, ha | (da0 + 512 * kb + 128 * k), hb | (db0 + 1024 * kb + 128 * k), k ? 1 : j);
    WG_COMMIT();
  }
  WG_WAIT(0);
  TS(10);
  store_half(oc, 0);
  store_half(oc + 32, 1);
  asm volatile(ELECT "cp.async.bulk.commit_group;\n@p cp.async.bulk.wait_group.read 0;\n}\n" ::: "memory");
  TS(wg * 16 + 11);
  GT(61 + wg);
  if (w == 0) TSDUMP(0);
  if (w == 1) TSDUMP(48);
}

typedef CUresult (*EncodeFn)(CUtensorMap*, CUtensorMapDataType, cuuint32_t, void*, const cuuint64_t*, const cuuint64_t*,
                             const cuuint32_t*, const cuuint32_t*, CUtensorMapInterleave, CUtensorMapSwizzle,
                             CUtensorMapL2promotion, CUtensorMapFloatOOBfill);

}

extern "C" void kernel_launch(void* const* d_in, const int* in_sizes, int n_in, void* d_out, int out_size) {
  (void)in_sizes; (void)n_in; (void)out_size;
  void* fn = nullptr;
  cudaDriverEntryPointQueryResult qr;
  cudaGetDriverEntryPoint("cuTensorMapEncodeTiled", &fn, cudaEnableDefault, &qr);
  EncodeFn enc = (EncodeFn)fn;
  CUtensorMap mx, mw, mo, mu, mout;
  const cuuint32_t es[5] = {1, 1, 1, 1, 1};
  {
    cuuint64_t dims[2] = {512, 2048}, st[1] = {1024};
    cuuint32_t box[2] = {64, 128};
    enc(&mx, CU_TENSOR_MAP_DATA_TYPE_BFLOAT16, 2, d_in[0], dims, st, box, es, CU_TENSOR_MAP_INTERLEAVE_NONE,
        CU_TENSOR_MAP_SWIZZLE_128B, CU_TENSOR_MAP_L2_PROMOTION_L2_128B, CU_TENSOR_MAP_FLOAT_OOB_FILL_NONE);
  }
  {
    cuuint64_t dims[3] = {512, 512, 3}, st[2] = {3072, 1024};
    cuuint32_t box[3] = {32, 64, 3};
    enc(&mw, CU_TENSOR_MAP_DATA_TYPE_BFLOAT16, 3, d_in[1], dims, st, box, es, CU_TENSOR_MAP_INTERLEAVE_NONE,
        CU_TENSOR_MAP_SWIZZLE_64B, CU_TENSOR_MAP_L2_PROMOTION_L2_128B, CU_TENSOR_MAP_FLOAT_OOB_FILL_NONE);
  }
  {
    cuuint64_t dims[3] = {64, 512, 8}, st[2] = {1024, 128};
    cuuint32_t box[3] = {64, 64, 2};
    enc(&mo, CU_TENSOR_MAP_DATA_TYPE_BFLOAT16, 3, d_in[3], dims, st, box, es, CU_TENSOR_MAP_INTERLEAVE_NONE,
        CU_TENSOR_MAP_SWIZZLE_128B, CU_TENSOR_MAP_L2_PROMOTION_L2_128B, CU_TENSOR_MAP_FLOAT_OOB_FILL_NONE);
  }
  {
    cuuint64_t dims[4] = {512, 4, 16, 32}, st[3] = {16384, 1024, 65536};
    cuuint32_t box[4] = {64, 4, 16, 2};
    enc(&mu, CU_TENSOR_MAP_DATA_TYPE_BFLOAT16, 4, d_in[4], dims, st, box, es, CU_TENSOR_MAP_INTERLEAVE_NONE,
        CU_TENSOR_MAP_SWIZZLE_128B, CU_TENSOR_MAP_L2_PROMOTION_L2_128B, CU_TENSOR_MAP_FLOAT_OOB_FILL_NONE);
  }
  {
    cuuint64_t dims[2] = {1024, 2048}, st[1] = {2048};
    cuuint32_t box[2] = {64, 16};
    enc(&mout, CU_TENSOR_MAP_DATA_TYPE_BFLOAT16, 2, d_out, dims, st, box, es, CU_TENSOR_MAP_INTERLEAVE_NONE,
        CU_TENSOR_MAP_SWIZZLE_128B, CU_TENSOR_MAP_L2_PROMOTION_NONE, CU_TENSOR_MAP_FLOAT_OOB_FILL_NONE);
  }
  Params P;
  P.x = (const __nv_bfloat16*)d_in[0];
  P.wphi = (const __nv_bfloat16*)d_in[2];
  P.wo = (const __nv_bfloat16*)d_in[3];
  P.logA = (const __nv_bfloat16*)d_in[5];
  P.Aim = (const __nv_bfloat16*)d_in[6];
  P.Cre = (const __nv_bfloat16*)d_in[7];
  P.Cim = (const __nv_bfloat16*)d_in[8];
  P.logdt = (const __nv_bfloat16*)d_in[9];
  P.Dskip = (const __nv_bfloat16*)d_in[10];
  P.out = (__nv_bfloat16*)d_out;
  cudaGetSymbolAddress((void**)&P.xs, g_x);
  P.ts = nullptr;
  cudaFuncSetAttribute(fused_kernel, cudaFuncAttributeMaxDynamicSharedMemorySize, SMEM_BYTES);
  fused_kernel<<<NCTA, NTHREADS, SMEM_BYTES>>>(P, mx, mw, mo, mu, mout);
}
```

```cpp
#include <cuda_runtime.h>
#include <cuda_bf16.h>
#include <cuda_fp16.h>
#include <cuda.h>
#include <stdint.h>
#include <type_traits>

#define DBG_TS 0

namespace {

constexpr int NTHREADS = 512;
constexpr int NCTA = 128;
constexpr int OFF_W = 0;
constexpr int OFF_X = 98304;
constexpr int OFF_U = OFF_X + 65536;
constexpr int U_CH = 4416, U_ODD = 2240, U_PAD = 128;
constexpr int OFF_STG0 = OFF_U + 18432;
constexpr int SLAB = 3328;
constexpr int OFF_T = OFF_STG0 + 8 * SLAB;
constexpr int T_CH = 5216;
constexpr int T_D = 0;
constexpr int T_5 = 2144;
constexpr int T_3 = T_5 + 384;
constexpr int T_7 = T_5 + 1024;
constexpr int T_9 = T_7 + 320;
constexpr int T_KC = T_9 + 320;
constexpr int T_ST = T_5 - 1024;
constexpr int OFF_PHI = OFF_T + 4 * T_CH;
constexpr int OFF_EYE = OFF_PHI + 1024, OFF_ONE = OFF_EYE + 512;
constexpr int OFF_BAR = OFF_ONE + 256;
constexpr int SMEM_BYTES = OFF_BAR + 512 + 256 * DBG_TS;
constexpr uint32_t SB = 1024;
static_assert(T_KC + 2 * 656 <= T_CH, "table size");
static_assert(SMEM_BYTES <= 232448, "smem");
constexpr int MB_URAW = 0, MB_FULL = 1  , MB_WO = 17, MB_UFULL = 18, MB_O = 19  ,
              MB_EMPTY = 23  , MB_AUX = 39;
__host__ __device__ constexpr uint32_t BAR(int i) { return SB + OFF_BAR + 8 * i; }
constexpr int NB_WG0 = 1, NB_ODONE = 2, NB_ST0 = 3, NB_HAND = 4, NB_KV = 5, NB_YZ = 6, NB_INIT = 7, NB_PREP = 8, NB_PROD = 9, NB_KREAD = 10,
              NB_BDONE = 11, NB_GATE = 12  , NB_Y = 7  ;
#define UAT 2
constexpr int U_AT = UAT;
constexpr int ZERO_STEP = 12;
constexpr int SPIN_MAX = 1 << 16;

constexpr int X_CNT = 0;
constexpr int X_PART = 256;
constexpr int X_O = X_PART + 16 * 8 * 144;
constexpr int X_Y = X_O + 32 * 32 * 128;
constexpr int X_UT = X_Y + 512 * 8 * 32;
constexpr int X_SIZE = X_UT + 512 * (U_CH / 16);
__device__ __align__(128) uint4 g_x[X_SIZE];
extern __shared__ uint8_t smem_raw[];
#define TS(i) do {} while (0)
#define TS1(i) do {} while (0)
#define GT(i) do {} while (0)
#define TSDUMP(base) do {} while (0)

__device__ __forceinline__ uint32_t smem_u32(const void* p) { return (uint32_t)__cvta_generic_to_shared(p); }
__device__ __forceinline__ void mbar_arrive(uint32_t b) {
  asm volatile("mbarrier.arrive.shared::cta.b64 _, [%0];" ::"r"(b) : "memory");
}
__device__ __forceinline__ void mbar_wait(uint32_t b) {
  uint32_t done = 0;
#pragma unroll 1
  for (int i = 0; i < SPIN_MAX && !done; i++) {
    asm volatile("{\n.reg .pred p;\nmbarrier.try_wait.parity.shared::cta.b64 p, [%1], 0, 4000;\nselp.u32 %0, 1, 0, p;\n}\n"
                 : "=r"(done) : "r"(b) : "memory");
  }
}
__device__ __forceinline__ void mbar_spin(uint32_t b) {
  uint32_t done = 0;
#pragma unroll 1
  for (int i = 0; i < (SPIN_MAX << 4) && !done; i++) {
    asm volatile("{\n.reg .pred p;\nmbarrier.try_wait.parity.shared::cta.b64 p, [%1], 0;\nselp.u32 %0, 1, 0, p;\n}\n"
                 : "=r"(done) : "r"(b) : "memory");
  }
}
__device__ __forceinline__ void mbar_init(uint32_t b, int n) {
  asm volatile("mbarrier.init.shared::cta.b64 [%0], %1;" ::"r"(b), "r"(n) : "memory");
}
__device__ __forceinline__ void mbar_expect(uint32_t b, int bytes) {
  asm volatile("mbarrier.arrive.expect_tx.shared::cta.b64 _, [%0], %1;" ::"r"(b), "r"(bytes) : "memory");
}
__device__ __forceinline__ void nb_sync(int id, int n) { asm volatile("bar.sync %0, %1;" ::"r"(id), "r"(n) : "memory"); }
__device__ __forceinline__ void nb_arrive(int id, int n) { asm volatile("bar.arrive %0, %1;" ::"r"(id), "r"(n) : "memory"); }
#define ELECT "{\n.reg .pred p;\nelect.sync _|p, 0xffffffff;\n@p "
__device__ __forceinline__ void e_arrive(uint32_t b) {
  asm volatile(ELECT "mbarrier.arrive.shared::cta.b64 _, [%0];\n}\n" ::"r"(b) : "memory");
}
__device__ __forceinline__ void e_expect(uint32_t b, int bytes) {
  asm volatile(ELECT "mbarrier.arrive.expect_tx.shared::cta.b64 _, [%0], %1;\n}\n" ::"r"(b), "r"(bytes) : "memory");
}
__device__ __forceinline__ void e_tma2d(uint32_t dst, const CUtensorMap* m, uint32_t bar, int c0, int c1) {
  asm volatile(ELECT "cp.async.bulk.tensor.2d.shared::cluster.global.mbarrier::complete_tx::bytes [%0], [%1, {%3,%4}], [%2];\n}\n"
               ::"r"(dst), "l"(m), "r"(bar), "r"(c0), "r"(c1) : "memory");
}
__device__ __forceinline__ void e_tma3d(uint32_t dst, const CUtensorMap* m, uint32_t bar, int c0, int c1, int c2) {
  asm volatile(ELECT "cp.async.bulk.tensor.3d.shared::cluster.global.mbarrier::complete_tx::bytes [%0], [%1, {%3,%4,%5}], [%2];\n}\n"
               ::"r"(dst), "l"(m), "r"(bar), "r"(c0), "r"(c1), "r"(c2) : "memory");
}
__device__ __forceinline__ void e_tma4d(uint32_t dst, const CUtensorMap* m, uint32_t bar, int c0, int c3) {
  asm volatile(ELECT "cp.async.bulk.tensor.4d.shared::cluster.global.mbarrier::complete_tx::bytes [%0], [%1, {%3,%5,%5,%4}], [%2];\n}\n"
               ::"r"(dst), "l"(m), "r"(bar), "r"(c0), "r"(c3), "r"(0) : "memory");
}
__device__ __forceinline__ void e_bulk(uint32_t dst, const void* src, int bytes, uint32_t bar) {
  asm volatile(ELECT "cp.async.bulk.shared::cluster.global.mbarrier::complete_tx::bytes [%0], [%1], %2, [%3];\n}\n"
               ::"r"(dst), "l"(src), "r"(bytes), "r"(bar) : "memory");
}
__device__ __forceinline__ void e_prefetch(const void* p, int bytes) {
  asm volatile(ELECT "cp.async.bulk.prefetch.L2.global [%0], %1;\n}\n" ::"l"(p), "r"(bytes) : "memory");
}
__device__ __forceinline__ void e_store2d(const CUtensorMap* m, uint32_t src, int c0, int c1) {
  asm volatile(ELECT "cp.async.bulk.tensor.2d.global.shared::cta.bulk_group [%0, {%2,%3}], [%1];\n}\n"
               ::"l"(m), "r"(src), "r"(c0), "r"(c1) : "memory");
}
__host__ __device__ constexpr uint64_t mkdesc(uint32_t addr, uint32_t lbo, uint32_t sbo, int swz) {
  return (uint64_t)((addr & 0x3FFFF) >> 4) | ((uint64_t)(lbo >> 4) << 16) | ((uint64_t)(sbo >> 4) << 32) |
         ((uint64_t)swz << 62);
}
#define SPLIT() asm volatile("{\n.reg .pred p;\nsetp.eq.u32 p, %0, %1;\n@p exit;\n}\n" ::"r"(blockIdx.y), "n"(__LINE__) : "memory")
#define SPLITN(n) asm volatile("{\n.reg .pred p;\nsetp.eq.u32 p, %0, %1;\n@p exit;\n}\n" ::"r"(blockIdx.y), "r"(4096 + (n)) : "memory")
#define WG_FENCE() asm volatile("wgmma.fence.sync.aligned;" ::: "memory")
#define WG_COMMIT() asm volatile("wgmma.commit_group.sync.aligned;" ::: "memory")
#define WG_WAIT(n) asm volatile("wgmma.wait_group.sync.aligned " #n ";" ::: "memory")

__device__ __forceinline__ void mma(float& d0, float& d1, float& d2, float& d3, uint32_t a0, uint32_t a1, uint32_t a2,
                                    uint32_t a3, uint32_t b0, uint32_t b1) {
  asm volatile("mma.sync.aligned.m16n8k16.row.col.f32.bf16.bf16.f32 {%0,%1,%2,%3},{%4,%5,%6,%7},{%8,%9},{%0,%1,%2,%3};"
               : "+f"(d0), "+f"(d1), "+f"(d2), "+f"(d3)
               : "r"(a0), "r"(a1), "r"(a2), "r"(a3), "r"(b0), "r"(b1));
}
__device__ __forceinline__ void mmac(float (&d)[4], uint32_t a0, uint32_t a1, uint32_t a2, uint32_t a3, uint32_t b0,
                                     uint32_t b1, const float (&c)[4]) {
  asm volatile("mma.sync.aligned.m16n8k16.row.col.f32.bf16.bf16.f32 {%0,%1,%2,%3},{%4,%5,%6,%7},{%8,%9},{%10,%11,%12,%13};"
               : "=f"(d[0]), "=f"(d[1]), "=f"(d[2]), "=f"(d[3])
               : "r"(a0), "r"(a1), "r"(a2), "r"(a3), "r"(b0), "r"(b1), "f"(c[0]), "f"(c[1]), "f"(c[2]), "f"(c[3]));
}
__device__ __forceinline__ void mma_h(float (&d)[4], const uint32_t (&a)[4], uint32_t b0, uint32_t b1) {
  asm volatile("mma.sync.aligned.m16n8k16.row.col.f32.f16.f16.f32 {%0,%1,%2,%3},{%4,%5,%6,%7},{%8,%9},{%0,%1,%2,%3};"
               : "+f"(d[0]), "+f"(d[1]), "+f"(d[2]), "+f"(d[3]) : "r"(a[0]), "r"(a[1]), "r"(a[2]), "r"(a[3]), "r"(b0), "r"(b1));
}
__device__ __forceinline__ void mma0(float& d0, float& d1, float& d2, float& d3, uint32_t a0, uint32_t a1, uint32_t a2,
                                     uint32_t a3, uint32_t b0, uint32_t b1) {
  asm volatile("mma.sync.aligned.m16n8k16.row.col.f32.bf16.bf16.f32 {%0,%1,%2,%3},{%4,%5,%6,%7},{%8,%9},{%10,%10,%10,%10};"
               : "=f"(d0), "=f"(d1), "=f"(d2), "=f"(d3)
               : "r"(a0), "r"(a1), "r"(a2), "r"(a3), "r"(b0), "r"(b1), "f"(0.f));
}
__device__ __forceinline__ uint32_t pack_bf(float lo, float hi) {
  uint32_t r;
  asm("cvt.rn.bf16x2.f32 %0, %1, %2;" : "=r"(r) : "f"(hi), "f"(lo));
  return r;
}
__device__ __forceinline__ float bf_lo(uint32_t w) { return __uint_as_float(w << 16); }
__device__ __forceinline__ float bf_hi(uint32_t w) { return __uint_as_float(w & 0xffff0000u); }
__device__ __forceinline__ float bf_round(float x) { return __bfloat162float(__float2bfloat16_rn(x)); }
__device__ __forceinline__ uint32_t bmax2(uint32_t a, uint32_t b) {
  uint32_t r; asm("max.bf16x2 %0, %1, %2;" : "=r"(r) : "r"(a), "r"(b)); return r;
}
__device__ __forceinline__ uint32_t bmin2(uint32_t a, uint32_t b) {
  uint32_t r; asm("min.bf16x2 %0, %1, %2;" : "=r"(r) : "r"(a), "r"(b)); return r;
}
__device__ __forceinline__ float ex2(float x) { float r; asm("ex2.approx.ftz.f32 %0, %1;" : "=f"(r) : "f"(x)); return r; }
__device__ __forceinline__ float rcp(float x) { float r; asm("rcp.approx.ftz.f32 %0, %1;" : "=f"(r) : "f"(x)); return r; }
__device__ __forceinline__ void ldsm4(uint32_t (&r)[4], uint32_t a) {
  asm volatile("ldmatrix.sync.aligned.m8n8.x4.shared.b16 {%0,%1,%2,%3}, [%4];"
               : "=r"(r[0]), "=r"(r[1]), "=r"(r[2]), "=r"(r[3]) : "r"(a) : "memory");
}
__device__ __forceinline__ void ldsm4t(uint32_t (&r)[4], uint32_t a) {
  asm volatile("ldmatrix.sync.aligned.m8n8.x4.trans.shared.b16 {%0,%1,%2,%3}, [%4];"
               : "=r"(r[0]), "=r"(r[1]), "=r"(r[2]), "=r"(r[3]) : "r"(a) : "memory");
}
__device__ __forceinline__ void stsm4(uint32_t a, uint32_t r0, uint32_t r1, uint32_t r2, uint32_t r3) {
  asm volatile("stmatrix.sync.aligned.m8n8.x4.shared.b16 [%0], {%1,%2,%3,%4};"
               ::"r"(a), "r"(r0), "r"(r1), "r"(r2), "r"(r3) : "memory");
}
__device__ __forceinline__ uint32_t lds32(uint32_t a) {
  uint32_t r; asm volatile("ld.shared.u32 %0, [%1];" : "=r"(r) : "r"(a) : "memory"); return r;
}
__device__ __forceinline__ uint32_t lds16(uint32_t a) {
  uint32_t r; asm volatile("{\n.reg .u16 h;\nld.shared.u16 h, [%1];\ncvt.u32.u16 %0, h;\n}\n" : "=r"(r) : "r"(a) : "memory"); return r;
}
__device__ __forceinline__ uint2 lds64(uint32_t a) {
  uint2 r; asm volatile("ld.shared.v2.u32 {%0,%1}, [%2];" : "=r"(r.x), "=r"(r.y) : "r"(a) : "memory"); return r;
}
__device__ __forceinline__ uint4 lds128(uint32_t a) {
  uint4 r;
  asm volatile("ld.shared.v4.u32 {%0,%1,%2,%3}, [%4];" : "=r"(r.x), "=r"(r.y), "=r"(r.z), "=r"(r.w) : "r"(a) : "memory");
  return r;
}
__device__ __forceinline__ void sts32(uint32_t a, uint32_t v) { asm volatile("st.shared.u32 [%0], %1;" ::"r"(a), "r"(v) : "memory"); }
__device__ __forceinline__ void sts16(uint32_t a, uint32_t v) {
  asm volatile("{\n.reg .u16 h;\ncvt.u16.u32 h, %1;\nst.shared.u16 [%0], h;\n}\n" ::"r"(a), "r"(v) : "memory");
}
__device__ __forceinline__ void sts64(uint32_t a, uint32_t x, uint32_t y) {
  asm volatile("st.shared.v2.u32 [%0], {%1,%2};" ::"r"(a), "r"(x), "r"(y) : "memory");
}
__device__ __forceinline__ void sts128(uint32_t a, uint32_t x, uint32_t y, uint32_t z, uint32_t w) {
  asm volatile("st.shared.v4.u32 [%0], {%1,%2,%3,%4};" ::"r"(a), "r"(x), "r"(y), "r"(z), "r"(w) : "memory");
}
__device__ __forceinline__ uint4 ld_x(const uint4* p) {
  uint4 r;
  asm volatile("{\n.reg .b128 t;\nld.relaxed.gpu.global.b128 t, [%4];\nmov.b128 {%0,%1,%2,%3}, t;\n}\n"
               : "=r"(r.x), "=r"(r.y), "=r"(r.z), "=r"(r.w) : "l"(p) : "memory");
  return r;
}
__device__ __forceinline__ uint32_t ld_x32(const uint32_t* p) {
  uint32_t r; asm volatile("ld.relaxed.gpu.global.u32 %0, [%1];" : "=r"(r) : "l"(p) : "memory"); return r;
}
__device__ __forceinline__ void st_x(uint4* p, uint32_t x, uint32_t y, uint32_t z, uint32_t w) {
  asm volatile("{\n.reg .b128 t;\nmov.b128 t, {%1,%2,%3,%4};\nst.relaxed.gpu.global.b128 [%0], t;\n}\n"
               ::"l"(p), "r"(x), "r"(y), "r"(z), "r"(w) : "memory");
}
__device__ __forceinline__ void st_x32(uint32_t* p, uint32_t x) {
  asm volatile("st.relaxed.gpu.global.u32 [%0], %1;" ::"l"(p), "r"(x) : "memory");
}
__device__ __forceinline__ uint32_t nz(uint32_t w) { return max(w, 1u); }
__device__ __forceinline__ uint32_t fu(float x) { return __float_as_uint(x); }
__device__ __forceinline__ float uf(uint32_t x) { return __uint_as_float(x); }

__device__ __forceinline__ void wgmma_ss_n96(float (&d)[48], uint64_t da, uint64_t db, int sc) {
  asm volatile("{\n.reg .pred p;\nsetp.ne.b32 p, %50, 0;\n"
      "wgmma.mma_async.sync.aligned.m64n96k16.f32.bf16.bf16 "
      "{%0,%1,%2,%3,%4,%5,%6,%7,%8,%9,%10,%11,%12,%13,%14,%15,%16,%17,%18,%19,%20,%21,%22,%23,%24,%25,%26,%27,%28,%29,%30,%31,%32,%33,%34,%35,%36,%37,%38,%39,%40,%41,%42,%43,%44,%45,%46,%47}, "
      "%48, %49, p, 1, 1, 0, 1;\n}\n"
      : "+f"(d[0]), "+f"(d[1]), "+f"(d[2]), "+f"(d[3]), "+f"(d[4]), "+f"(d[5]), "+f"(d[6]), "+f"(d[7]),
        "+f"(d[8]), "+f"(d[9]), "+f"(d[10]), "+f"(d[11]), "+f"(d[12]), "+f"(d[13]), "+f"(d[14]), "+f"(d[15]),
        "+f"(d[16]), "+f"(d[17]), "+f"(d[18]), "+f"(d[19]), "+f"(d[20]), "+f"(d[21]), "+f"(d[22]), "+f"(d[23]),
        "+f"(d[24]), "+f"(d[25]), "+f"(d[26]), "+f"(d[27]), "+f"(d[28]), "+f"(d[29]), "+f"(d[30]), "+f"(d[31]),
        "+f"(d[32]), "+f"(d[33]), "+f"(d[34]), "+f"(d[35]), "+f"(d[36]), "+f"(d[37]), "+f"(d[38]), "+f"(d[39]),
        "+f"(d[40]), "+f"(d[41]), "+f"(d[42]), "+f"(d[43]), "+f"(d[44]), "+f"(d[45]), "+f"(d[46]), "+f"(d[47])
      : "l"(da), "l"(db), "r"(sc));
}

__device__ __forceinline__ void wgmma_ss_n128(float (&d)[64], uint64_t da, uint64_t db, int sc) {
  asm volatile("{\n.reg .pred p;\nsetp.ne.b32 p, %66, 0;\n"
      "wgmma.mma_async.sync.aligned.m64n128k16.f32.bf16.bf16 "
      "{%0,%1,%2,%3,%4,%5,%6,%7,%8,%9,%10,%11,%12,%13,%14,%15,%16,%17,%18,%19,%20,%21,%22,%23,%24,%25,%26,%27,%28,%29,%30,%31,%32,%33,%34,%35,%36,%37,%38,%39,%40,%41,%42,%43,%44,%45,%46,%47,%48,%49,%50,%51,%52,%53,%54,%55,%56,%57,%58,%59,%60,%61,%62,%63}, "
      "%64, %65, p, 1, 1, 0, 1;\n}\n"
      : "+f"(d[0]), "+f"(d[1]), "+f"(d[2]), "+f"(d[3]), "+f"(d[4]), "+f"(d[5]), "+f"(d[6]), "+f"(d[7]),
        "+f"(d[8]), "+f"(d[9]), "+f"(d[10]), "+f"(d[11]), "+f"(d[12]), "+f"(d[13]), "+f"(d[14]), "+f"(d[15]),
        "+f"(d[16]), "+f"(d[17]), "+f"(d[18]), "+f"(d[19]), "+f"(d[20]), "+f"(d[21]), "+f"(d[22]), "+f"(d[23]),
        "+f"(d[24]), "+f"(d[25]), "+f"(d[26]), "+f"(d[27]), "+f"(d[28]), "+f"(d[29]), "+f"(d[30]), "+f"(d[31]),
        "+f"(d[32]), "+f"(d[33]), "+f"(d[34]), "+f"(d[35]), "+f"(d[36]), "+f"(d[37]), "+f"(d[38]), "+f"(d[39]),
        "+f"(d[40]), "+f"(d[41]), "+f"(d[42]), "+f"(d[43]), "+f"(d[44]), "+f"(d[45]), "+f"(d[46]), "+f"(d[47]),
        "+f"(d[48]), "+f"(d[49]), "+f"(d[50]), "+f"(d[51]), "+f"(d[52]), "+f"(d[53]), "+f"(d[54]), "+f"(d[55]),
        "+f"(d[56]), "+f"(d[57]), "+f"(d[58]), "+f"(d[59]), "+f"(d[60]), "+f"(d[61]), "+f"(d[62]), "+f"(d[63])
      : "l"(da), "l"(db), "r"(sc));
}

__device__ __forceinline__ void wgmma_ss_n40(float (&d)[20], uint64_t da, uint64_t db, int sc) {
  asm volatile("{\n.reg .pred p;\nsetp.ne.b32 p, %22, 0;\n"
      "wgmma.mma_async.sync.aligned.m64n40k16.f32.bf16.bf16 "
      "{%0,%1,%2,%3,%4,%5,%6,%7,%8,%9,%10,%11,%12,%13,%14,%15,%16,%17,%18,%19}, "
      "%20, %21, p, 1, 1, 1, 1;\n}\n"
      : "+f"(d[0]), "+f"(d[1]), "+f"(d[2]), "+f"(d[3]), "+f"(d[4]), "+f"(d[5]), "+f"(d[6]), "+f"(d[7]),
        "+f"(d[8]), "+f"(d[9]), "+f"(d[10]), "+f"(d[11]), "+f"(d[12]), "+f"(d[13]), "+f"(d[14]), "+f"(d[15]),
        "+f"(d[16]), "+f"(d[17]), "+f"(d[18]), "+f"(d[19])
      : "l"(da), "l"(db), "r"(sc));
}

__device__ __forceinline__ void wgmma_rs_n8(float (&d)[4], const uint4& a, uint64_t db, int sc) {
  asm volatile("{\n.reg .pred p;\nsetp.ne.b32 p, %9, 0;\n"
      "wgmma.mma_async.sync.aligned.m64n8k16.f32.bf16.bf16 "
      "{%0,%1,%2,%3}, "
      "{%4,%5,%6,%7}, %8, p, 1, 1, 1;\n}\n"
      : "+f"(d[0]), "+f"(d[1]), "+f"(d[2]), "+f"(d[3])
      : "r"(a.x), "r"(a.y), "r"(a.z), "r"(a.w), "l"(db), "r"(sc));
}

__device__ __forceinline__ void wgmma_rs_n16(float (&d)[8], const uint4& a, uint64_t db, int sc) {
  asm volatile("{\n.reg .pred p;\nsetp.ne.b32 p, %13, 0;\n"
      "wgmma.mma_async.sync.aligned.m64n16k16.f32.bf16.bf16 "
      "{%0,%1,%2,%3,%4,%5,%6,%7}, "
      "{%8,%9,%10,%11}, %12, p, 1, 1, 1;\n}\n"
      : "+f"(d[0]), "+f"(d[1]), "+f"(d[2]), "+f"(d[3]), "+f"(d[4]), "+f"(d[5]), "+f"(d[6]), "+f"(d[7])
      : "r"(a.x), "r"(a.y), "r"(a.z), "r"(a.w), "l"(db), "r"(sc));
}

__device__ __forceinline__ void wgmma_rs_n24(float (&d)[12], const uint4& a, uint64_t db, int sc) {
  asm volatile("{\n.reg .pred p;\nsetp.ne.b32 p, %17, 0;\n"
      "wgmma.mma_async.sync.aligned.m64n24k16.f32.bf16.bf16 "
      "{%0,%1,%2,%3,%4,%5,%6,%7,%8,%9,%10,%11}, "
      "{%12,%13,%14,%15}, %16, p, 1, 1, 1;\n}\n"
      : "+f"(d[0]), "+f"(d[1]), "+f"(d[2]), "+f"(d[3]), "+f"(d[4]), "+f"(d[5]), "+f"(d[6]), "+f"(d[7]),
        "+f"(d[8]), "+f"(d[9]), "+f"(d[10]), "+f"(d[11])
      : "r"(a.x), "r"(a.y), "r"(a.z), "r"(a.w), "l"(db), "r"(sc));
}

struct Params {
  const __nv_bfloat16 *logA, *Aim, *Cre, *Cim, *logdt, *Dskip, *x, *wphi, *wo;
  __nv_bfloat16* out;
  uint4* xs;
  long long* ts;
};

__device__ __forceinline__ uint4 tr_row(const uint4 (&v)[8], int i) {
  uint32_t o[4];
#pragma unroll
  for (int m = 0; m < 4; m++) {
    const uint4 &ra = v[2 * m], &rb = v[2 * m + 1];
    const int k = i >> 1;
    const uint32_t xa = k == 0 ? ra.x : k == 1 ? ra.y : k == 2 ? ra.z : ra.w;
    const uint32_t xb = k == 0 ? rb.x : k == 1 ? rb.y : k == 2 ? rb.z : rb.w;
    o[m] = __byte_perm(xa, xb, (i & 1) ? 0x7632 : 0x5410);
  }
  return make_uint4(o[0], o[1], o[2], o[3]);
}

struct cpx { float r, i; };
__device__ __forceinline__ cpx csq(cpx a) { return {a.r * a.r - a.i * a.i, 2.f * (a.r * a.i)}; }
__device__ __forceinline__ cpx polar(float e, float t) {
  const float m = ex2(e);
  return {m * __cosf(t), m * __sinf(t)};
}

struct KgenRaw { uint32_t la, ai, cr, ci, ldt; };
__device__ __forceinline__ KgenRaw kgen_load(const Params& P, int d, int unit, int lane, int on) {
  const int o = d * 64 + unit * 32 + lane;
  KgenRaw r = {0, 0, 0, 0, 0};
  asm volatile("{\n.reg .pred p;\nsetp.ne.b32 p, %10, 0;\n@p ld.global.nc.u32 %0, [%5];\n@p ld.global.nc.u32 %1, [%6];\n"
               "@p ld.global.nc.u32 %2, [%7];\n@p ld.global.nc.u32 %3, [%8];\n@p ld.global.nc.u16 %4, [%9];\n}\n"
               : "+r"(r.la), "+r"(r.ai), "+r"(r.cr), "+r"(r.ci), "+r"(r.ldt)
               : "l"((const uint32_t*)P.logA + o), "l"((const uint32_t*)P.Aim + o), "l"((const uint32_t*)P.Cre + o),
                 "l"((const uint32_t*)P.Cim + o), "l"(P.logdt + d), "r"(on));
  return r;
}
struct hc { __half2 r, i; };
struct cpx2 { cpx a, b; };
__device__ __forceinline__ cpx2 csq2(const cpx2& v) { return {csq(v.a), csq(v.b)}; }
__device__ __forceinline__ hc toh(const cpx2& v) { return {__floats2half2_rn(v.a.r, v.b.r), __floats2half2_rn(v.a.i, v.b.i)}; }
__device__ __forceinline__ hc hmul(const hc& z, const hc& w) {
  return {__hfma2(z.r, w.r, __hneg2(__hmul2(z.i, w.i))), __hfma2(z.r, w.i, __hmul2(z.i, w.r))};
}
__device__ __forceinline__ hc hmulc(const hc& z, const hc& w) {
  return {__hfma2(z.r, w.r, __hmul2(z.i, w.i)), __hfma2(z.i, w.r, __hneg2(__hmul2(z.r, w.i)))};
}
__device__ __forceinline__ uint32_t hu(__half2 v) { return *(const uint32_t*)&v; }
__device__ __forceinline__ __half2 uh(uint32_t v) { return *(const __half2*)&v; }

struct KgenAddr { uint32_t sa[2], ld[5][4]; };
__device__ __forceinline__ KgenAddr kgen_addr(int lane, uint32_t buf) {
  KgenAddr a;
  a.sa[0] = buf + (lane & 7) * 128 + ((((lane >> 3) ^ lane) & 7) << 4);
  a.sa[1] = a.sa[0] ^ 64;
  const int q = lane >> 4;
  const uint32_t b = buf + ((lane >> 3) & 1) * 1024 + q * 128;
  const int e[5] = {lane & 7, 0, 1, 2 + (lane & 1), 4 + (lane & 3)};
#pragma unroll
  for (int i = 0; i < 20; i++) {
    a.ld[i >> 2][i & 3] = b + ((e[i >> 2] ^ q ^ (2 * (i & 3))) << 4);
    asm volatile("" : "+r"(a.ld[i >> 2][i & 3]));
  }
  asm volatile("" : "+r"(a.sa[0]), "+r"(a.sa[1]));
  return a;
}
__device__ __forceinline__ void kgen_unit(const KgenRaw& r, const KgenAddr& ad, uint32_t zero, float (&k)[5][4], float& k2048, float& sc) {
  const float dt = bf_round(expf(bf_lo(r.ldt)));
  const uint32_t ar = pack_bf(ex2(bf_lo(r.la) * 1.4426950408889634f), ex2(bf_hi(r.la) * 1.4426950408889634f));
  const float ca = dt * -1.4426950408889634f, a0 = bf_lo(ar) * ca, a1 = bf_hi(ar) * ca;
  const float f0 = bf_lo(r.ai) * dt, f1 = bf_hi(r.ai) * dt;
  const float r0 = f0 * 20.21267777267071f, r1 = f1 * 20.21267777267071f;
  const uint32_t cm = __vmaxu2(r.cr & 0x7fff7fffu, r.ci & 0x7fff7fffu);
  const uint32_t ex = min(max(__reduce_max_sync(0xffffffffu, max(cm >> 16, cm & 0xffffu)) >> 7, 1u), 253u);
  const float cs = uf((254u - ex) << 23);
  sc = 2.f * dt * uf(ex << 23);
  const cpx2 C = {{bf_lo(r.cr) * cs, bf_lo(r.ci) * -cs}, {bf_hi(r.cr) * cs, bf_hi(r.ci) * -cs}};
  auto put = [&](const hc (&v)[8]) {
    stsm4(ad.sa[0], hu(v[0].r), hu(v[1].r), hu(v[2].r), hu(v[3].r));
    stsm4(ad.sa[0] + 1024, hu(v[0].i), hu(v[1].i), hu(v[2].i), hu(v[3].i));
    stsm4(ad.sa[1], hu(v[4].r), hu(v[5].r), hu(v[6].r), hu(v[7].r));
    stsm4(ad.sa[1] + 1024, hu(v[4].i), hu(v[5].i), hu(v[6].i), hu(v[7].i));
    __syncwarp();
  };
  auto get = [&](uint32_t (&o)[4][4], const uint32_t (&a)[4]) {
#pragma unroll
    for (int i = 0; i < 4; i++) ldsm4(o[i], a[i] + i * 256);
  };
  auto at = [](const uint32_t (&o)[4][4], int s) { return hc{uh(o[s >> 1][2 * (s & 1)]), uh(o[s >> 1][2 * (s & 1) + 1])}; };
  uint32_t A[8][4];
  auto tile = [&](int j, const uint32_t (&B)[4][4]) {
    k[j][0] = k[j][1] = k[j][2] = k[j][3] = 0.f;
#pragma unroll
    for (int s = 0; s < 8; s++) mma_h(k[j], A[s], B[s >> 1][2 * (s & 1)], B[s >> 1][2 * (s & 1) + 1]);
  };
  const cpx2 w1 = {polar(a0, f0), polar(a1, f1)};
  const cpx2 w127 = {polar(a0 * 127.f, (r0 - rintf(r0)) * 6.283185307179586f), polar(a1 * 127.f, (r1 - rintf(r1)) * 6.283185307179586f)};
  const cpx2 w2 = csq2(w1), w4 = csq2(w2);
  uint32_t T0[4][4], X[4][4], M[3][4][4];
  {
    hc t[8];
    t[0] = {uh(0x3C003C00u), uh(0u)}; t[1] = toh(w1); t[2] = toh(w2); t[4] = toh(w4);
    t[3] = hmul(t[1], t[2]); t[5] = hmul(t[1], t[4]); t[6] = hmul(t[2], t[4]); t[7] = hmul(t[3], t[4]);
    put(t); get(T0, ad.ld[0]);
  }
  SPLIT();
  const cpx2 w8 = csq2(w4), w16 = csq2(w8), w32 = csq2(w16), w64 = csq2(w32);
  {
    const hc m8 = toh(w8), m16 = toh(w16), m32 = toh(w32);
    hc a[8];
    a[0] = toh(C); a[1] = hmulc(a[0], m8);
    a[2] = hmulc(a[0], m16); a[3] = hmulc(a[1], m16);
#pragma unroll
    for (int i = 0; i < 4; i++) a[4 + i] = hmulc(a[i], m32);
    put(a); get(X, ad.ld[0]);
  }
  SPLIT();
    const cpx2 w128 = {{w127.a.r * w1.a.r - w127.a.i * w1.a.i, w127.a.r * w1.a.i + w127.a.i * w1.a.r},
                     {w127.b.r * w1.b.r - w127.b.i * w1.b.i, w127.b.r * w1.b.i + w127.b.i * w1.b.r}};
  const cpx2 w256 = csq2(w128), w512 = csq2(w256);
  const hc m128 = toh(w128), m256 = toh(w256), m512 = toh(w512);
  {
    const hc m254 = toh(csq2(w127)), m127 = toh(w127);
    hc m[8];
    m[0] = toh(w64); m[1] = m128; m[2] = m256; m[3] = hmul(m127, m256);
    m[4] = m512; m[5] = hmul(m127, m512); m[6] = hmul(m[4], m254); m[7] = hmul(m[5], m254);
    put(m);
    get(M[0], ad.ld[1]);
#pragma unroll
    for (int s = 0; s < 8; s++) {
      const hc z = at(X, s), y = hmulc(z, at(M[0], s));
      A[s][0] = hu(z.r) + zero; A[s][1] = hu(y.r); A[s][2] = hu(z.i) + zero; A[s][3] = hu(y.i);
    }
#pragma unroll
    for (int i = 0; i < 3; i++) get(M[i], ad.ld[i + 2]);
  }
  SPLIT();
  tile(0, T0);
  const cpx2 w1024 = csq2(w512), we = csq2(w1024);
  {
    hc t[8];
    t[0] = toh(w1024); t[1] = hmul(t[0], m128);
    t[2] = hmul(t[0], m256); t[3] = hmul(t[1], m256);
#pragma unroll
    for (int i = 0; i < 4; i++) t[4 + i] = hmul(t[i], m512);
    put(t); get(X, ad.ld[0]);
  }
  k2048 = (C.a.r * we.a.r + C.a.i * we.a.i + C.b.r * we.b.r + C.b.i * we.b.i) * sc;
#pragma unroll
  for (int j = 1; j < 5; j++) k[j][0] = k[j][1] = k[j][2] = k[j][3] = 0.f;
#pragma unroll
  for (int s = 0; s < 8; s++) {
#pragma unroll
    for (int j = 0; j < 3; j++) {
      const hc y = hmul(at(T0, s), at(M[j], s));
      mma_h(k[1 + j], A[s], hu(y.r), hu(y.i));
    }
    mma_h(k[4], A[s], X[s >> 1][2 * (s & 1)], X[s >> 1][2 * (s & 1) + 1]);
  }
}

__device__ __forceinline__ void build_tables(uint32_t tb, int lane, float (&k)[5][4], float k2048) {
  const int g = lane >> 2, c = lane & 3;
  const uint32_t kc = tb + T_KC + 16;
  {
    const uint32_t a0 = kc + 16 * g + 4 * c, a2 = kc + 2 * (256 + 4 * g + c);
    const uint32_t a3 = kc + 2 * (384 + 2 * g + 64 * (c & 1) + (c >> 1)), a4 = kc + 2 * (512 + g + 32 * c);
#pragma unroll
    for (int r = 0; r < 2; r++) {
      sts32(a0 + 128 * r, pack_bf(k[0][2 * r], k[0][2 * r + 1]));
      sts32(a0 + 128 * r + 256, pack_bf(k[1][2 * r], k[1][2 * r + 1]));
      const uint32_t w2 = pack_bf(k[2][2 * r], k[2][2 * r + 1]);
      const uint32_t w3 = pack_bf(k[3][2 * r], k[3][2 * r + 1]);
      const uint32_t w4 = pack_bf(k[4][2 * r], k[4][2 * r + 1]);
      sts16(a2 + 64 * r, w2); sts16(a2 + 64 * r + 128, w2 >> 16);
      sts16(a3 + 32 * r, w3); sts16(a3 + 32 * r + 64, w3 >> 16);
      sts16(a4 + 16 * r, w4); sts16(a4 + 16 * r + 32, w4 >> 16);
    }
  }
  if (lane == 0) { sts16(kc + 2 * 640, pack_bf(k2048, 0.f)); sts32(kc - 4, 0); }
  __syncwarp();
  const uint32_t td = tb + T_D + 32;
#pragma unroll
  for (int hf = 0; hf < 2; hf++) {
    const uint2 v = lds64(kc + 256 * hf + 8 * lane);
    const uint32_t pv = lds32(kc + 256 * hf + 8 * lane - 4);
    sts128(td + 512 * hf + 16 * lane, __byte_perm(v.x, pv, 0x7610), __byte_perm(v.x, v.x, 0x1032), __byte_perm(v.y, v.x, 0x7610),
           __byte_perm(v.y, v.y, 0x1032));
  }
#pragma unroll
  for (int hf = 0; hf < 2; hf++) {
    const uint32_t v = lds32(kc + 512 + 128 * hf + 4 * lane), nx = lds32(kc + 516 + 128 * hf + 4 * lane);
    uint32_t w0 = __byte_perm(v, v, 0x1010);
    const uint32_t w1 = w0;
    if (hf == 0) { const uint32_t pv = lds32(kc + 508); if (lane == 0) w0 = __byte_perm(v, pv, 0x7610); }
    sts128(td + 1024 + 512 * hf + 16 * lane, w0, w1, __byte_perm(v, v, 0x1032), __byte_perm(nx, v, 0x7610));
  }
  {
    const uint32_t kk = lds16(kc + 2 * 384);
    const uint32_t w = lane < 3 ? (kk | (kk << 16)) : (lane == 3 ? (kk << 16) : 0u);
    if (lane < 24) sts32(td + 4 * (lane < 16 ? 512 + lane : lane - 24), w);
    const uint32_t lo_ = lds16(kc + 2 * 511), le_ = lds16(kc + 2 * 512);
    const uint32_t ja = tb + T_5 + (lane < 16 ? 4 * lane : 256 + 4 * lane);
    sts32(ja, lane == 16 ? (le_ << 16) : 0u);
    sts32(ja + 384, lane == 16 ? (lo_ << 16) : 0u);
    sts32(tb + (lane < 16 ? T_7 : T_9 - 64) + 4 * lane, 0u);
  }
#pragma unroll
  for (int s = 0; s < 2; s++) {
    const uint32_t b = kc + 2 * (s ? 512 : 384) + 8 * lane;
    const uint2 v = lds64(b);
    uint32_t em = lds16(b - 2), e0 = v.x;
    const uint32_t e4 = lds16(b + 8);
    if (lane == 0) { em = 0; e0 = 0; }
    sts64(tb + (s ? T_7 : T_3) + 64 + 8 * lane, __byte_perm(v.x, em, 0x5432), __byte_perm(v.y, v.x, 0x7632));
    sts64(tb + (s ? T_9 : T_5) + 64 + 8 * lane, __byte_perm(v.y, e0, 0x5410), __byte_perm(e4, v.y, 0x5410));
  }
  __syncwarp();
}

__device__ __forceinline__ uint32_t box2w(int lo, int n, int o) {
  return ((unsigned)(o - lo) < (unsigned)n ? 0x3F80u : 0u) | ((unsigned)(o + 1 - lo) < (unsigned)n ? 0x3F800000u : 0u);
}

__device__ __forceinline__ void conv_channel(uint32_t ub, uint32_t tb, int lane, uint4* ydst) {
  const int g = lane >> 2, c = lane & 3, x = g - 2 * c;
  const int mi = lane >> 3;
  const uint32_t qa = ub + U_PAD + 16 * (lane & 7) + ((mi == 0 || mi == 3) ? U_ODD : 0) - (mi == 0 ? 16 : 0);
  const uint32_t hb = ub + U_PAD + (mi & 1) * U_ODD + 16 * ((lane >> 4) + (lane & 7)) - 16;
  const uint32_t kv = lds16(tb + T_KC + 16 + 2 * 512);
  const int oh = c < 2 ? 8 + 2 * c : 2 * c - 8, og = c < 3 ? 2 * c : -10;
  uint32_t bx[4] = {box2w(g - 4, 9, 2 * c), box2w(g - 3, 7, 2 * c), box2w(g - 4, 9, oh), box2w(g - 3, 7, oh)};
  uint32_t by[4] = {box2w(g - 10, 5, 2 * c - 8), box2w(g - 5, 3, 2 * c - 8), box2w(g - 10, 5, og), box2w(g - 5, 3, og)};
  uint32_t lb0 = ((unsigned)(x + 5) < 2u ? kv : 0u) | ((unsigned)(x + 4) < 2u ? kv << 16 : 0u);
  uint32_t lb1 = ((unsigned)(x - 3) < 2u ? kv : 0u) | ((unsigned)(x - 4) < 2u ? kv << 16 : 0u);
  const int q0 = g - 1, q1 = c < 3 ? g : g - 2;
  uint32_t y0a = ub + U_PAD + (q0 & 1) * U_ODD + 16 * (q0 >> 1) + 4 * c;
  uint32_t y1a = ub + U_PAD + (q1 & 1) * U_ODD + 16 * (q1 >> 1) + 4 * c;
#pragma unroll
  for (int i = 0; i < 4; i++) asm volatile("" : "+r"(bx[i]), "+r"(by[i]));
  asm volatile("" : "+r"(lb0), "+r"(lb1), "+r"(y0a), "+r"(y1a));
  mbar_wait(BAR(MB_UFULL));
  mbar_spin(BAR(MB_EMPTY + 15));
  TS(36);
  float acc[16][4];
  {
    uint32_t z09[8], z07[8], zm9[8], zm7[8];
#pragma unroll
    for (int i = 0; i < 8; i++) {
      uint32_t h[4];
      ldsm4(h, hb + 128 * i);
      float y0, y1, y2, y3, w0, w1, w2, w3;
      mma0(y0, y1, y2, y3, bx[0], bx[1], bx[2], bx[3], h[2], c < 2 ? h[3] : h[1]);
      mma0(w0, w1, w2, w3, bx[0], bx[1], bx[2], bx[3], h[1], c < 2 ? h[2] : h[0]);
      z09[i] = pack_bf(y0, y1); z07[i] = pack_bf(y2, y3);
      zm9[i] = pack_bf(w0, w1); zm7[i] = pack_bf(w2, w3);
    }
  uint32_t f3[3][4][4];
  {
    const uint32_t fa = tb + T_7 + 4 * (16 + x);
#pragma unroll
    for (int tt = 0; tt < 3; tt++)
#pragma unroll
      for (int D = 0; D < 4; D++) {
        const uint32_t a = fa + (tt == 0 ? 316 : (tt == 1 ? 320 : 0)) + 64 * D;
        f3[tt][D][0] = lds32(a); f3[tt][D][1] = lds32(a + 32); f3[tt][D][2] = lds32(a - 32); f3[tt][D][3] = lds32(a);
      }
  }
    SPLIT();
    nb_sync(NB_GATE, 256);
    SPLIT();
    float a[4][2][4];
#pragma unroll
    for (int kap = 0; kap < 4; kap++)
#pragma unroll
      for (int sg = 0; sg < 2; sg++)
#pragma unroll
        for (int bk = 3; bk >= kap; bk--) {
          const uint32_t(&q0_)[4] = f3[sg ? 2 : 0][bk - kap];
          const uint32_t(&q1_)[4] = f3[sg ? 2 : 1][bk - kap];
          float(&a0)[4] = a[bk][0];
          float(&a1)[4] = a[bk][1];
          if (sg == 0 && kap == 0) {
            mma0(a0[0], a0[1], a0[2], a0[3], q0_[0], q0_[1], q0_[2], q0_[3], z09[0], z09[1]);
            mma0(a1[0], a1[1], a1[2], a1[3], q1_[0], q1_[1], q1_[2], q1_[3], zm9[0], zm9[1]);
          } else {
            mma(a0[0], a0[1], a0[2], a0[3], q0_[0], q0_[1], q0_[2], q0_[3], sg ? zm7[2 * kap] : z09[2 * kap], sg ? zm7[2 * kap + 1] : z09[2 * kap + 1]);
            mma(a1[0], a1[1], a1[2], a1[3], q1_[0], q1_[1], q1_[2], q1_[3], sg ? z07[2 * kap] : zm9[2 * kap], sg ? z07[2 * kap + 1] : zm9[2 * kap + 1]);
          }
        }
    SPLIT();
#pragma unroll
    for (int i = 0; i < 8; i++) {
      uint32_t h[4];
      ldsm4(h, qa + 128 * i);
      const float ci[4] = {a[i >> 1][0][2 * (i & 1)], a[i >> 1][0][2 * (i & 1) + 1], a[i >> 1][1][2 * (i & 1)], a[i >> 1][1][2 * (i & 1) + 1]};
      mmac(acc[8 + i], h[0], h[1], h[2], h[3], lb0, lb1, ci);
    }
  }
  TS(44);
  {
    uint2 a5[10], a3[10];
    const uint32_t aa = tb + T_5 + 4 * (8 + 2 * g - 2 * c);
#pragma unroll
    for (int m = 0; m < 10; m++) { a5[m] = lds64(aa + 32 * m); a3[m] = lds64(aa + 384 + 32 * m); }
    uint32_t x5[12][2], x3[12][2];
    auto ygen = [&](int kap) {
#pragma unroll
      for (int hh = 0; hh < 2; hh++) {
        float y0, y1, y2, y3;
        mma0(y0, y1, y2, y3, by[0], by[1], by[2], by[3], lds32(y0a + 128 * kap + 64 * hh), lds32(y1a + 128 * kap + 64 * hh));
        x5[kap][hh] = pack_bf(y0, y1);
        x3[kap][hh] = pack_bf(y2, y3);
      }
    };
    ygen(11); ygen(10); ygen(9); ygen(8);
#pragma unroll
    for (int kap = 11; kap >= 0; kap--) {
      if (kap >= 4) ygen(kap - 4);
#pragma unroll
      for (int sg = 0; sg < 2; sg++)
#pragma unroll
        for (int i = 4; i >= 0; i--) {
          const int be = kap + 4 + i;
          if (be <= 15) {
            const uint2 &hi = sg ? a3[2 * i + 1] : a5[2 * i + 1], &lo = sg ? a3[2 * i] : a5[2 * i];
            const uint32_t b0 = sg ? x3[kap][0] : x5[kap][0], b1 = sg ? x3[kap][1] : x5[kap][1];
            if (be < 8 && i == 0 && sg == 0) mma0(acc[be][0], acc[be][1], acc[be][2], acc[be][3], hi.x, hi.y, lo.x, lo.y, b0, b1);
            else mma(acc[be][0], acc[be][1], acc[be][2], acc[be][3], hi.x, hi.y, lo.x, lo.y, b0, b1);
          }
        }
    }
  }
  TS(45);
  {
    const uint32_t st = tb + T_ST + lane * 8;
#pragma unroll
    for (int be = 4; be < 12; be++) sts64(st + 256 * be, pack_bf(acc[be][0], acc[be][1]), pack_bf(acc[be][2], acc[be][3]));
    SPLIT();
    uint32_t F[66], qd[8][4];
    const uint32_t fa = tb + T_D + 32 + 4 * x;
#pragma unroll
    for (int i = 0; i < 32; i++) {
      const int s = 120 - (i >> 2) - 8 * (i & 3);
      uint32_t(&q)[4] = qd[i & 7];
      ldsm4(q, qa + 16 * s);
      const int m = 16 * (i & 3) + 2 * (i >> 2);
      F[m] = lds32(fa + 32 * m); F[m + 1] = lds32(fa + 32 * m + 32);
#pragma unroll
      for (int be = 15; be >= 12; be--) {
        const int de = 8 * be - s;
        float(&a)[4] = (be >= 14 && !(i & 1)) ? acc[be - 4] : acc[be];
        if (de >= 0 && be >= 14 && i == 2 * (15 - be)) mma0(a[0], a[1], a[2], a[3], q[0], q[1], q[2], q[3], F[2 * de + 1], F[2 * de]);
        else if (de >= 0) mma(a[0], a[1], a[2], a[3], q[0], q[1], q[2], q[3], F[2 * de + 1], F[2 * de]);
      }
    }
#pragma unroll
    for (int i = 0; i < 8; i++) acc[14 + (i >> 2)][i & 3] += acc[10 + (i >> 2)][i & 3];
    F[64] = lds32(fa + 32 * 64); F[65] = lds32(fa + 32 * 65);
#pragma unroll
    for (int i = 0; i < 6; i++) ldsm4(qd[i], qa + 128 * 11 - 16 * i);
    uint2 sv = lds64(st + 256 * 11);
    float ci[4] = {bf_lo(sv.x), bf_hi(sv.x), bf_lo(sv.y), bf_hi(sv.y)};
    float T[5][4];
#pragma unroll
    for (int i = 0; i < 16; i++) T[i >> 2][i & 3] = acc[12 + (i >> 2)][i & 3];
    nb_sync(NB_YZ, 160);
    TS(46);
    uint32_t held[2];
#pragma unroll
    for (int be = 11; be >= 0; be--) {
      if (be & 1) SPLITN(be);
      const uint32_t qp = qa + 128 * be;
#pragma unroll
      for (int k = 4; k >= 1; k--) mmac(T[k], qd[0][0], qd[0][1], qd[0][2], qd[0][3], F[16 * k + 1], F[16 * k], T[k - 1]);
      if (be >= 4) mmac(T[0], qd[0][0], qd[0][1], qd[0][2], qd[0][3], F[1], F[0], ci);
      else mma0(T[0][0], T[0][1], T[0][2], T[0][3], qd[0][0], qd[0][1], qd[0][2], qd[0][3], F[1], F[0]);
      ldsm4(qd[6], qp - 16 * 6);
      ldsm4(qd[7], qp - 16 * 7);
      if (be > 4) sv = lds64(st + 256 * (be - 1));
#pragma unroll
      for (int i = 1; i < 8; i++) {
#pragma unroll
        for (int k = 3; k >= 0; k--)
          mma(T[k][0], T[k][1], T[k][2], T[k][3], qd[i][0], qd[i][1], qd[i][2], qd[i][3], F[16 * k + 2 * i + 1], F[16 * k + 2 * i]);
        if (i < 7 && be > 0) ldsm4(qd[i - 1], qp - 128 - 16 * (i - 1));
        if (i == 2) {
          const uint32_t w0 = pack_bf(T[4][0], T[4][1]), w1 = pack_bf(T[4][2], T[4][3]);
          if (be & 1) { held[0] = w0; held[1] = w1; }
          else st_x(ydst + (be + 4) * 16, nz(w0), w1, held[0], held[1]);
          if ((be & 3) == 3 && be < 11) nb_arrive(NB_Y + 2 + (be >> 2), 160);
        }
        if (i == 4 && be > 4) { ci[0] = bf_lo(sv.x); ci[1] = bf_hi(sv.x); ci[2] = bf_lo(sv.y); ci[3] = bf_hi(sv.y); }
      }
    }
    if ((fu(T[0][0]) & fu(T[1][0]) & fu(T[2][0]) & fu(T[3][0])) == 0xffffffffu) sts32(st, 0);
    nb_arrive(NB_BDONE, 288);
    nb_arrive(NB_Y + 1, 160);
#pragma unroll
    for (int B = 1; B >= 0; B--)
      st_x(ydst + B * 32, nz(pack_bf(T[2 * B][0], T[2 * B][1])), pack_bf(T[2 * B][2], T[2 * B][3]),
           pack_bf(T[2 * B + 1][0], T[2 * B + 1][1]), pack_bf(T[2 * B + 1][2], T[2 * B + 1][3]));
  }
}

__device__ __forceinline__ void dual_exp(const uint32_t* w, uint32_t* e) {
  const float L = 1.44268798828125f;
  uint32_t mx = bmax2(bmax2(w[0], w[1]), bmax2(w[2], w[3]));
  uint32_t mn = bmin2(bmin2(w[0], w[1]), bmin2(w[2], w[3]));
  mx = bmax2(mx, __shfl_xor_sync(0xffffffffu, mx, 1));
  mn = bmin2(mn, __shfl_xor_sync(0xffffffffu, mn, 1));
  mx = bmax2(mx, __shfl_xor_sync(0xffffffffu, mx, 2));
  mn = bmin2(mn, __shfl_xor_sync(0xffffffffu, mn, 2));
  const float mx0 = bf_lo(mx) * -L, mx1 = bf_hi(mx) * -L, mn0 = bf_lo(mn) * L, mn1 = bf_hi(mn) * L;
#pragma unroll
  for (int i = 0; i < 2; i++) {
    const float a0 = bf_lo(w[2 * i]), a1 = bf_hi(w[2 * i]), b0 = bf_lo(w[2 * i + 1]), b1 = bf_hi(w[2 * i + 1]);
    e[2 * i] = pack_bf(ex2(fmaf(a0, L, mx0)), ex2(fmaf(b0, L, mx0)));
    e[2 * i + 1] = pack_bf(ex2(fmaf(a1, L, mx1)), ex2(fmaf(b1, L, mx1)));
    e[4 + 2 * i] = pack_bf(ex2(fmaf(a0, -L, mn0)), ex2(fmaf(b0, -L, mn0)));
    e[5 + 2 * i] = pack_bf(ex2(fmaf(a1, -L, mn1)), ex2(fmaf(b1, -L, mn1)));
  }
}
__device__ __forceinline__ void normalise(uint32_t* e, const float (&s)[4]) {
  const uint32_t r = pack_bf(rcp(s[0]), rcp(s[2]));
  const __nv_bfloat162 rr = *(const __nv_bfloat162*)&r;
#pragma unroll
  for (int i = 0; i < 4; i++) {
    const __nv_bfloat162 v = __hmul2(*(const __nv_bfloat162*)&e[i], (i & 1) ? __high2bfloat162(rr) : __low2bfloat162(rr));
    e[i] = *(const uint32_t*)&v;
  }
}
__host__ __device__ constexpr uint64_t qdesc(uint32_t addr) { return mkdesc(addr, 128, 256, 0); }

__global__ void __launch_bounds__(NTHREADS, 1)
fused_kernel(const Params P, const __grid_constant__ CUtensorMap mx, const __grid_constant__ CUtensorMap mw,
             const __grid_constant__ CUtensorMap mo, const __grid_constant__ CUtensorMap mu,
             const __grid_constant__ CUtensorMap mout, const __grid_constant__ CUtensorMap mut) {
  constexpr uint32_t sb = SB;
  const int tid = threadIdx.x, lane = tid & 31;
  const int warp = __shfl_sync(0xffffffffu, tid >> 5, 0);
  const int b = blockIdx.x, oct = b >> 3, i8 = b & 7;
  const int rt = (((oct & 4) ? ~oct : oct) & 3) * 2 + (i8 >> 2);
  const int hp = (oct >> 2) * 4 + (i8 & 3);

  const int wg = warp >> 2, w = warp & 3;
  const int d = b * 4 + ((tid >> 5) & 3);
  const KgenRaw raw = kgen_load(P, d, (tid >> 7) & 1, lane, (tid + 128) & 256);
  const uint32_t tb = sb + OFF_T + w * T_CH;
  if (warp >= 12) {
    asm volatile("setmaxnreg.dec.sync.aligned.u32 32;");
    if (warp == 12) {
      if (lane == 0) {
#pragma unroll
        for (int i = 0; i < 9; i++) mbar_init(BAR(i), 1);
        asm volatile("fence.mbarrier_init.release.cluster;" ::: "memory");
      }
      __syncwarp();
      if (lane < 9) mbar_expect(BAR(0) + 8 * lane, lane == 0 ? 16384 : 28672);
      __syncwarp();
      nb_arrive(NB_PROD, 384);
#pragma unroll 1
      for (int kb = 0; kb < 8; kb++) {
        if (kb == U_AT) e_tma4d(sb + OFF_STG0, &mu, BAR(MB_URAW), i8 * 64, oct * 2);
        e_tma3d(sb + OFF_W + kb * 12288, &mw, BAR(MB_FULL) + 8 * kb, hp * 32, kb * 64, 0);
        if (kb < 5) e_tma2d(sb + OFF_X + (kb < 2 ? kb + 3 : kb - 2) * 16384, &mx, BAR(MB_FULL) + 8 * kb, kb * 64, rt * 256);
      }
      if (U_AT == 8) e_tma4d(sb + OFF_STG0, &mu, BAR(MB_URAW), i8 * 64, oct * 2);
      if (smem_u32(smem_raw) != SB) __trap();
      if (lane == 0) TS1(54);
      nb_sync(NB_GATE + 1, 64);
      e_prefetch(P.x + (size_t)(rt * 256 + 128 + hp * 8) * 512, 8192);
      uint32_t slot = sb + OFF_X + 3 * 16384;
#pragma unroll 1
      for (int n = 0; n < 11; n++) {
        mbar_spin(BAR(MB_EMPTY) + 8 * n);
        const int m = n + 5;
        e_tma2d(slot, &mx, BAR(MB_FULL) + 8 * m, (m & 7) * 64, rt * 256 + (m >> 3) * 128);
        slot = slot == sb + OFF_X + 4 * 16384 ? sb + OFF_X : slot + 16384;
        if (n == 7) {
          e_prefetch(P.wo + (size_t)b * 2048, 4096);
          asm volatile("prefetch.tensormap [%0];" ::"l"(&mo) : "memory");
          asm volatile("prefetch.tensormap [%0];" ::"l"(&mout) : "memory");
        }
      }
      mbar_wait(BAR(MB_UFULL));
#pragma unroll 1
      for (int i = 0; i < 8; i++) {
        mbar_wait(BAR(MB_EMPTY + 10) + 8 * ((0x54332222u >> (4 * i)) & 7));
        const int w0 = (0x54736210u >> (4 * i)) & 7;
        e_tma3d(sb + OFF_W + w0 * 16384, &mo, BAR(MB_WO), 0, w0 * 64, (hp & 3) * 2);
      }
    } else {
      if (warp == 13) {
        if (lane == 0) {
#pragma unroll
          for (int i = 9; i < 40; i++) mbar_init(BAR(i), (i < MB_EMPTY || i == MB_AUX) ? 1 : 4);
          asm volatile("fence.mbarrier_init.release.cluster;" ::: "memory");
        }
        __syncwarp();
        if (lane < 14 && lane != 9) mbar_expect(BAR(MB_FULL + 8) + 8 * lane, lane == 8 ? 131072 : (lane == 10 ? 8192 : (lane == 13 ? 24576 : 16384)));
        nb_arrive(NB_GATE + 1, 64);
      } else if (warp == 14) {
        asm volatile("prefetch.tensormap [%0];" ::"l"(&mw) : "memory");
        asm volatile("prefetch.tensormap [%0];" ::"l"(&mx) : "memory");
        asm volatile("prefetch.tensormap [%0];" ::"l"(&mu) : "memory");
        asm volatile("prefetch.tensormap [%0];" ::"l"(&mut) : "memory");
        e_prefetch(P.x + (size_t)(rt * 256 + hp * 8) * 512, 8192);
      }
      nb_sync(NB_PROD, 384);
      if (warp == 15) {
        const uint4 v0 = __ldg((const uint4*)P.wphi + hp * 64 + lane), v1 = __ldg((const uint4*)P.wphi + hp * 64 + 32 + lane);
        sts128(sb + OFF_PHI + (lane & 1) * 256 + (lane >> 1) * 16, v0.x, v0.y, v0.z, v0.w);
        sts128(sb + OFF_PHI + 512 + (lane & 1) * 256 + (lane >> 1) * 16, v1.x, v1.y, v1.z, v1.w);
        const uint32_t one = (((lane >> 3) ^ (lane >> 4)) & 1) ? 0u : ((lane & 1) ? 0x3F800000u : 0x3F80u);
        const int q = (lane >> 1) & 3;
        sts128(sb + OFF_EYE + lane * 16, q == 0 ? one : 0u, q == 1 ? one : 0u, q == 2 ? one : 0u, q == 3 ? one : 0u);
        sts64(sb + OFF_ONE + lane * 8, 0x3F803F80u, 0x3F803F80u);
        asm volatile("fence.proxy.async.shared::cta;" ::: "memory");
        nb_arrive(NB_KREAD, 160);
      }
      uint32_t* cnt = (uint32_t*)(P.xs + X_CNT) + (warp == 13 ? i8 : (warp == 14 ? 8 + rt : 16 + oct)) * 32;
      const unsigned target = (ld_x32(cnt) & ~15u) + 16;
      if (warp != 14) {
        if (warp == 15) mbar_wait(BAR(MB_EMPTY + ZERO_STEP));
        uint4* pz = P.xs + (warp == 13 ? X_PART + (hp * 8 + rt) * 144 : X_Y + b * 1024) + lane;
#pragma unroll 1
        for (int i = (warp == 13 ? 144 : 1024) - lane; i > 0; i -= 32, pz += 32) st_x(pz, 0, 0, 0, 0);
      }
      if (warp == 15) __syncwarp();
      else nb_sync(warp == 13 ? NB_INIT : NB_ODONE, warp == 13 ? 160 : 288);
      if (warp == 13) {
        if (lane == 0) TS1(49);
        if (lane == 0) {
          asm volatile("cp.async.bulk.tensor.3d.global.shared::cta.bulk_group [%0, {%2,%4,%3}], [%1];\n"
                       "cp.async.bulk.commit_group;\ncp.async.bulk.wait_group 0;\nfence.proxy.async.global;\n"
                       ::"l"(&mut), "r"(sb + OFF_STG0), "r"(oct * 64), "r"(i8 * 64), "r"(0) : "memory");
          mbar_arrive(BAR(MB_AUX));
        }
      }
      if (lane == 0) asm volatile("red.release.gpu.global.add.u32 [%0], %1;" ::"l"(cnt), "r"(warp == 15 ? 2 : 1) : "memory");
      if (lane == 0) TS1(warp == 13 ? 50 : (warp == 14 ? 57 : 53));
      __syncwarp();
      if (warp == 14) nb_arrive(NB_GATE + 1, 160);
      asm volatile("fence.proxy.async.shared::cta;" ::: "memory");
      if (warp == 13) cnt += ((lane & 1 ? b >> 4 : i8 ^ (lane & 4)) - i8) * 32;
#pragma unroll 1
      for (int i = 0; i < SPIN_MAX; i++) {
        unsigned v;
        asm volatile("ld.acquire.gpu.global.u32 %0, [%1];" : "=r"(v) : "l"(cnt) : "memory");
        if (__all_sync(0xffffffffu, (int)(v - target) >= 0)) break;
      }
      if (lane == 0) TS1(warp == 13 ? 51 : (warp == 14 ? 58 : 55));
      if (warp == 15) { nb_arrive(NB_YZ, 160); return; }
      asm volatile("fence.proxy.async.global;" ::: "memory");
      if (warp == 13) {
        mbar_wait(BAR(MB_EMPTY + 11));
        e_expect(BAR(MB_UFULL), 4 * U_CH);
        e_bulk(sb + OFF_U, P.xs + X_UT + b * (U_CH / 4), 4 * U_CH, BAR(MB_UFULL));
      } else {
        const uint4* src = P.xs + X_O + (rt * 4 + (hp >> 2)) * 4096;
        e_bulk(sb + OFF_X + 32768 + 57344, src + 3584, 8192, BAR(MB_O));
        e_bulk(sb + OFF_X + 32768, src, 16384, BAR(MB_O + 1));
        e_bulk(sb + OFF_X + 49152, src + 1024, 16384, BAR(MB_O + 2));
        e_bulk(sb + OFF_STG0, src + 3200, 6144, BAR(MB_O + 3));
        nb_sync(NB_BDONE, 288);
        asm volatile("fence.proxy.async.shared::cta;" ::: "memory");
        e_bulk(sb + OFF_U, src + 2048, 18432, BAR(MB_O + 3));
      }
    }
    return;
  }

  asm volatile("setmaxnreg.inc.sync.aligned.u32 160;");
  const int t = tid & 127;
  const int g = lane >> 2, c = lane & 3;
  const uint32_t kp = ((tb + 127) & ~127u) + (wg & 1) * 2048;
  const KgenAddr kad = kgen_addr(lane, kp);
  if (wg) nb_sync(NB_PROD, 384);
  SPLIT();
  float k[5][4], k2048, ksc;
  if (wg) {
    kgen_unit(raw, kad, blockIdx.y, k, k2048, ksc);
    TS(40 + wg);
    if ((fu(k[0][0]) & fu(k[1][0]) & fu(k[2][0]) & fu(k[3][0]) & fu(k[4][0])) == 0xffffffffu) sts32(kp, 0);
  }
  if (wg) nb_arrive(0, 384);
  if (wg) {
    if (wg == 1) {
      uint32_t h[10];
#pragma unroll
      for (int j = 0; j < 10; j++) h[j] = hu(__floats2half2_rn(k[j >> 1][2 * (j & 1)], k[j >> 1][2 * (j & 1) + 1]));
      sts128(kp + lane * 16, h[0], h[1], h[2], h[3]);
      sts128(kp + 512 + lane * 16, h[4], h[5], h[6], h[7]);
      sts128(kp + 1024 + lane * 16, h[8], h[9], fu(k2048), fu(ksc));
      nb_arrive(NB_PREP, 256);
    }
  } else {
    nb_sync(NB_KREAD, 160);
  }
  if (wg == 1) {
    mbar_wait(BAR(MB_URAW));
    TS(48);
    const int ln = ((lane >> 1) & 3) + 4 * (lane & 1);
    uint32_t r[8][4];
#pragma unroll
    for (int i = 0; i < 8; i++) ldsm4t(r[i], sb + OFF_STG0 + w * 4096 + ((lane >> 3) * 8 + ln) * 128 + ((i ^ ln) << 4));
    nb_sync(NB_HAND, 128);
    const uint32_t dst = sb + OFF_STG0 + (2 * g + (w & 1)) * 128 + ((((w >> 1) * 4 + c) ^ ((2 * g + (w & 1)) & 7)) << 4);
#pragma unroll
    for (int i = 0; i < 8; i++) sts128(dst + i * 2048, r[i][0], r[i][1], r[i][2], r[i][3]);
    asm volatile("fence.proxy.async.shared::cta;" ::: "memory");
    nb_arrive(NB_INIT, 160);
  }
  {
    if (wg == 2) {
#pragma unroll
      for (int j = 0; j < 5; j++) { k[j][0] *= ksc; k[j][1] *= ksc; k[j][2] *= ksc; k[j][3] *= ksc; }
      const unsigned short dsk = __ldg((const unsigned short*)P.Dskip + d);
      nb_sync(NB_PREP, 256);
      {
        const uint32_t src = kp + 2048 + lane * 16;
        const uint4 v0 = lds128(src), v1 = lds128(src + 512), v2 = lds128(src + 1024);
        const uint32_t h[10] = {v0.x, v0.y, v0.z, v0.w, v1.x, v1.y, v1.z, v1.w, v2.x, v2.y};
#pragma unroll
        for (int j = 0; j < 10; j++) {
          const float2 f = __half22float2(*(const __half2*)&h[j]);
          k[j >> 1][2 * (j & 1)] = fmaf(f.x, uf(v2.w), k[j >> 1][2 * (j & 1)]);
          k[j >> 1][2 * (j & 1) + 1] = fmaf(f.y, uf(v2.w), k[j >> 1][2 * (j & 1) + 1]);
        }
        k2048 += uf(v2.z);
      }
#pragma unroll
      for (int o2 = 16; o2; o2 >>= 1) k2048 += __shfl_xor_sync(0xffffffffu, k2048, o2);
      if (lane == 0) k[0][0] += bf_lo(dsk);
      __syncwarp();
      TS(34);
      build_tables(tb, lane, k, k2048);
      TS(35);
      uint4* const g_y = P.xs + X_Y;
      conv_channel(sb + OFF_U + w * U_CH, tb, lane, g_y + (size_t)d * 256 + lane);
      nb_arrive(NB_Y, 160);
      TS(37);
      if (w == 0) TSDUMP(32);
      return;
    }
    if (wg == 1) {
      mbar_wait(BAR(MB_EMPTY + 4));
      mbar_spin(BAR(MB_EMPTY + 6));
    }
    TS(wg * 16 + 1);
  }

  float acc[2][48];
  {
    uint32_t fb = BAR(MB_FULL) + 64 * wg;
    uint32_t da = (uint32_t)mkdesc(sb + OFF_X, 16, 0, 0) + (wg ? 1024 : 3072), db = (uint32_t)mkdesc(sb + OFF_W, 4096, 0, 0);
    constexpr uint64_t ha = mkdesc(0, 0, 1024, 1), hb = mkdesc(0, 0, 512, 2);
    mbar_spin(fb);
    if (wg == 0) nb_sync(0, 384);
    TS(wg * 16 + 2);
#pragma unroll 1
    for (int kb = 0; kb < 8; kb++) {
      WG_FENCE();
#pragma unroll
      for (int k = 0; k < 4; k++) {
        wgmma_ss_n96(acc[0], ha | (da + 2 * k), hb | (db + 64 * k), k ? 1 : kb);
        wgmma_ss_n96(acc[1], ha | (da + 2 * k + 512), hb | (db + 64 * k), k ? 1 : kb);
      }
      WG_COMMIT();
      if (kb < 7) mbar_spin(fb + 8);
      WG_WAIT(1);
      if (kb > 0) e_arrive(fb + 8 * (MB_EMPTY - MB_FULL - 1));
      fb += 8; db += 768;
      da = da == (uint32_t)mkdesc(sb + OFF_X + 65536, 16, 0, 0) ? da - 4096 : da + 1024;
    }
    WG_WAIT(0);
    e_arrive(fb + 8 * (MB_EMPTY - MB_FULL - 1));
    SPLIT();
  }
  TS(wg * 16 + 3);

  constexpr uint32_t stg0 = sb + OFF_STG0, stg1 = sb + OFF_X + 32768;
  uint4* const g_part = P.xs + X_PART;
  uint4* const g_o = P.xs + X_O;
  constexpr uint32_t kvs = stg0;
  auto pack8 = [](const float* a) { return make_uint4(pack_bf(a[0], a[1]), pack_bf(a[2], a[3]), pack_bf(a[4], a[5]), pack_bf(a[6], a[7])); };
  auto stage_k = [&](auto nt, const uint4* af, const uint4* vp, uint32_t sl, uint32_t free_bar) {
    constexpr int NU = 2 * decltype(nt)::value;
    float p[NU][8], rs[2 * NU][4];
    uint32_t ek[8 * NU];
    WG_FENCE();
#pragma unroll
    for (int u = 0; u < NU; u++) wgmma_rs_n16(p[u], af[u], qdesc(sb + OFF_PHI + (u & 1) * 512), 0);
    WG_COMMIT();
    WG_WAIT(0);
#pragma unroll
    for (int u = 0; u < NU; u++) {
      const uint32_t pw[4] = {pack_bf(p[u][0], p[u][2]), pack_bf(p[u][1], p[u][3]), pack_bf(p[u][4], p[u][6]), pack_bf(p[u][5], p[u][7])};
      dual_exp(pw, ek + 8 * u);
    }
    TS(wg * 16 + 12);
    mbar_spin(free_bar);
    WG_FENCE();
#pragma unroll
    for (int i = 0; i < 2 * NU; i++) wgmma_rs_n8(rs[i], make_uint4(ek[4 * i], ek[4 * i + 1], ek[4 * i + 2], ek[4 * i + 3]), qdesc(sb + OFF_ONE), 0);
    WG_COMMIT();
#pragma unroll
    for (int i = 0; i < NU; i++) stsm4(sl + (i >> 1) * 4 * SLAB + 2048 + (i & 1) * 512, vp[i].x, vp[i].y, vp[i].z, vp[i].w);
    if (NU == 4 || lane < 16) sts128(sl + (lane >> 4) * (4 * SLAB - 256) + 3072, 0x3F803F80u, 0x3F803F80u, 0x3F803F80u, 0x3F803F80u);
    WG_WAIT(0);
#pragma unroll
    for (int i = 0; i < 2 * NU; i++) {
      normalise(ek + 4 * i, rs[i]);
      stsm4(sl + (i >> 2) * 4 * SLAB + (i & 3) * 512, ek[4 * i], ek[4 * i + 1], ek[4 * i + 2], ek[4 * i + 3]);
    }
    asm volatile("fence.proxy.async.shared::cta;" ::: "memory");
  };
  auto contract = [&](float (&kc)[20], uint32_t stg, int acc_in) {
    WG_FENCE();
#pragma unroll
    for (int s = 0; s < 8; s++) wgmma_ss_n40(kc, qdesc(stg + s * SLAB), qdesc(stg + s * SLAB + 2048), s ? 1 : acc_in);
    WG_COMMIT();
    WG_WAIT(0);
  };
  uint32_t eq[32];
  {
    uint4 af[4], aq[4], vp[4];
    float kc[20];
#pragma unroll
    for (int u = 0; u < 4; u++) { af[u] = pack8(acc[u >> 1] + 16 + 8 * (u & 1)); vp[u] = pack8(acc[u >> 1] + 32 + 8 * (u & 1)); }
    const uint32_t hand = stg1 + 16384 + 8192 + w * 2048 + lane * 16;
    if (wg) {
      sts128(hand, af[2].x, af[2].y, af[2].z, af[2].w); sts128(hand + 512, af[3].x, af[3].y, af[3].z, af[3].w);
      sts128(hand + 1024, vp[2].x, vp[2].y, vp[2].z, vp[2].w); sts128(hand + 1536, vp[3].x, vp[3].y, vp[3].z, vp[3].w);
      nb_arrive(NB_HAND, 256);
    }
#pragma unroll
    for (int u = 0; u < 4; u++) aq[u] = pack8(acc[u >> 1] + 8 * (u & 1));
    if (wg == 0) {
      stage_k(std::integral_constant<int, 2>(), af, vp, stg0 + w * SLAB + lane * 16, BAR(MB_AUX));
      TS(13);
      nb_sync(NB_WG0, 128);
      contract(kc, stg0, 0);
      mbar_wait(BAR(MB_UFULL));
      TS(15);
      nb_sync(NB_HAND, 256);
      af[0] = lds128(hand); af[1] = lds128(hand + 512); vp[0] = lds128(hand + 1024); vp[1] = lds128(hand + 1536);
      nb_sync(NB_WG0, 128);
    }
    stage_k(std::integral_constant<int, 1>(), af, vp, stg1 + (wg ? w : 4 + w) * SLAB + lane * 16, BAR(MB_EMPTY + 15));
    TS(wg * 16 + 14);
    float p[4][8];
    if (wg) {
      nb_arrive(NB_ST0, 256);
      nb_arrive(NB_GATE, 256);
    } else {
      uint4* pp = g_part + (size_t)(hp * 8 + rt) * 144 + t;
      uint32_t* pz = (uint32_t*)(pp - t + 128) + w * 16 + c * 8 + g;
      asm volatile("" : "+l"(pp), "+l"(pz));
      nb_sync(NB_ST0, 256);
      contract(kc, stg1, 1);
      TS(6);
      float kv[8];
#pragma unroll
      for (int i = 0; i < 8; i++) kv[i] = w & 2 ? kc[8 + i] : kc[i];
      st_x(pp, nz(pack_bf(kv[0], kv[1])), pack_bf(kv[2], kv[3]), pack_bf(kv[4], kv[5]), pack_bf(kv[6], kv[7]));
      if (c < 2) st_x32(pz, nz(fu(c ? kc[18] : kc[16])));
      TS(5);
    }
    SPLIT();
    WG_FENCE();
#pragma unroll
    for (int u = 0; u < 4; u++) wgmma_rs_n16(p[u], aq[u], qdesc(sb + OFF_PHI + (u & 1) * 512), 0);
    WG_COMMIT();
    WG_WAIT(0);
#pragma unroll
    for (int u = 0; u < 4; u++) {
      const uint32_t pw[4] = {pack_bf(p[u][0], p[u][2]), pack_bf(p[u][1], p[u][3]), pack_bf(p[u][4], p[u][6]), pack_bf(p[u][5], p[u][7])};
      dual_exp(pw, eq + 8 * u);
    }
    SPLIT();
  }
  TS(wg * 16 + 4);
  if (wg == 1) {
    mbar_wait(BAR(MB_UFULL));
    const uint4* ps = g_part + (size_t)hp * 8 * 144 + t;
    const uint32_t* zs = (const uint32_t*)(g_part + (size_t)(hp * 8 + (lane >> 4) * 4) * 144 + 128) + w * 16 + (lane & 15);
    uint4 v[8];
    uint32_t zv[4];
#pragma unroll 1
    for (int it = 0; it < SPIN_MAX; it++) {
#pragma unroll
      for (int i = 0; i < 8; i++) v[i] = ld_x(ps + i * 144);
#pragma unroll
      for (int i = 0; i < 4; i++) zv[i] = ld_x32(zs + i * 576);
      uint32_t m = min(min(zv[0], zv[1]), min(zv[2], zv[3]));
#pragma unroll
      for (int i = 0; i < 8; i++) m = min(m, v[i].x);
      if (__all_sync(0xffffffffu, m != 0)) break;
    }
    float s[8];
    WG_FENCE();
#pragma unroll
    for (int r = 0; r < 8; r++) wgmma_rs_n16(s, v[r], qdesc(sb + OFF_EYE), r);
    WG_COMMIT();
    float zsum = (uf(zv[0]) + uf(zv[1])) + (uf(zv[2]) + uf(zv[3]));
    zsum += __shfl_xor_sync(0xffffffffu, zsum, 16);
    const uint32_t z1 = pack_bf(zsum, 1.f);
    if (lane < 16) sts128(kvs + w * 768 + 512 + lane * 16, z1, z1, z1, z1);
    WG_WAIT(0);
    stsm4(kvs + w * 768 + lane * 16, pack_bf(s[0], s[1]), pack_bf(s[2], s[3]), pack_bf(s[4], s[5]), pack_bf(s[6], s[7]));
    asm volatile("fence.proxy.async.shared::cta;" ::: "memory");
    TS(22);
  }
  nb_sync(NB_KV, 256);
  {
    float n[8][12];
    WG_FENCE();
#pragma unroll
    for (int i = 0; i < 8; i++) wgmma_rs_n24(n[i], make_uint4(eq[4 * i], eq[4 * i + 1], eq[4 * i + 2], eq[4 * i + 3]), qdesc(kvs + (i & 3) * 768), 0);
    WG_COMMIT();
    uint32_t* od = (uint32_t*)(g_o + (size_t)((rt * 4 + wg * 2) * 32 + hp * 2) * 128) + w * 64 + lane;
    WG_WAIT(0);
#pragma unroll
    for (int u = 0; u < 4; u++) {
      float(&np)[12] = n[2 * u];
      const float(&nm)[12] = n[2 * u + 1];
      const float q0 = np[9] * rcp(nm[9]), q1 = np[11] * rcp(nm[11]);
      const float r0 = rcp(fmaf(nm[8], q0, fmaf(np[9], 1e-6f, np[8]))), r1 = rcp(fmaf(nm[10], q1, fmaf(np[11], 1e-6f, np[10])));
#pragma unroll
      for (int i = 0; i < 8; i++) np[i] = fmaf(nm[i], (i & 2) ? q1 : q0, np[i]);
      uint32_t* o = od + (u >> 1) * 16384 + (u & 1) * 512;
      o[0] = pack_bf(np[0] * r0, np[1] * r0);
      o[32] = pack_bf(np[2] * r1, np[3] * r1);
      o[256] = pack_bf(np[4] * r0, np[5] * r0);
      o[288] = pack_bf(np[6] * r1, np[7] * r1);
      if (u == 1) SPLIT();
    }
  }
  TS(wg * 16 + 7);
  nb_arrive(NB_ODONE, 288);
  if (wg) {
    const uint4* src = P.xs + X_Y + (oct * 32 + c * 8) * 256 + (2 * w + (g >> 2)) * 32 + i8 * 4 + (g & 3);
    __nv_bfloat16* dst = P.out + (size_t)((2 * w + (g >> 2)) * 256 + i8 * 16 + (g & 3) * 2) * 1024 + 512 + oct * 32 + c * 8;
    nb_sync(NB_GATE + 1, 160);
    nb_sync(NB_Y + w, 160);
    uint4 v[8];
#pragma unroll 1
    for (int it = 0; it < SPIN_MAX; it++) {
      uint32_t m = 0xffffffffu;
#pragma unroll
      for (int i = 0; i < 8; i++) v[i] = ld_x(src + i * 256);
#pragma unroll
      for (int i = 0; i < 8; i++) m = min(m, v[i].x);
      if (__all_sync(0xffffffffu, m != 0)) break;
    }
#pragma unroll
    for (int i = 0; i < 8; i++) *(uint4*)(dst + (size_t)((i >> 2) * 128 + ((i >> 1) & 1) * 8 + (i & 1)) * 1024) = tr_row(v, i);
    TS(31);
    GT(63);
    if (w == 0) TSDUMP(16);
    return;
  }
  mbar_wait(BAR(MB_WO));
  nb_sync(NB_BDONE, 288);
  TS(8);
  mbar_spin(BAR(MB_O));
  TS(9);
  constexpr uint64_t ha = mkdesc(0, 0, 128, 0), hb = mkdesc(0, 0, 1024, 1);
  constexpr uint32_t da0 = (uint32_t)mkdesc(stg1, 1024, 0, 0), db0 = (uint32_t)mkdesc(sb + OFF_W, 8192, 0, 0);
  const uint32_t ot = ((sb + OFF_T + 1023) & ~1023u) + w * 4096;
  auto store_half = [&](const float* oc, int hf) {
#pragma unroll
    for (int i = 0; i < 8; i += 2)
      stsm4(ot + hf * 2048 + (lane & 15) * 128 + (((i + (lane >> 4)) ^ lane) & 7) * 16, pack_bf(oc[4 * i], oc[4 * i + 1]),
            pack_bf(oc[4 * i + 2], oc[4 * i + 3]), pack_bf(oc[4 * i + 4], oc[4 * i + 5]), pack_bf(oc[4 * i + 6], oc[4 * i + 7]));
    asm volatile("fence.proxy.async.shared::cta;" ::: "memory");
    __syncwarp();
    e_store2d(&mout, ot + hf * 2048, (hp & 3) * 128 + hf * 64, (rt * 4 + (hp >> 2)) * 64 + w * 16);
  };
  float oc[64];
#pragma unroll 1
  for (int j = 0; j < 8; j++) {
    const int kb = (j + 7) & 7;
    if ((j & 1) && j < 6) mbar_spin(BAR(MB_O + 1) + 4 * (j - 1));
    WG_FENCE();
#pragma unroll
    for (int k = 0; k < 4; k++) wgmma_ss_n128(oc, ha | (da0 + 512 * kb + 128 * k), hb | (db0 + 1024 * kb + 128 * k), k ? 1 : j);
    WG_COMMIT();
  }
  WG_WAIT(0);
  TS(10);
  store_half(oc, 0);
  store_half(oc + 32, 1);
  asm volatile(ELECT "cp.async.bulk.commit_group;\n@p cp.async.bulk.wait_group.read 0;\n}\n" ::: "memory");
  TS(wg * 16 + 11);
  GT(61 + wg);
  if (w == 0) TSDUMP(0);
  if (w == 1) TSDUMP(48);
}

typedef CUresult (*EncodeFn)(CUtensorMap*, CUtensorMapDataType, cuuint32_t, void*, const cuuint64_t*, const cuuint64_t*,
                             const cuuint32_t*, const cuuint32_t*, CUtensorMapInterleave, CUtensorMapSwizzle,
                             CUtensorMapL2promotion, CUtensorMapFloatOOBfill);

}

extern "C" void kernel_launch(void* const* d_in, const int* in_sizes, int n_in, void* d_out, int out_size) {
  (void)in_sizes; (void)n_in; (void)out_size;
  void* fn = nullptr;
  cudaDriverEntryPointQueryResult qr;
  cudaGetDriverEntryPoint("cuTensorMapEncodeTiled", &fn, cudaEnableDefault, &qr);
  EncodeFn enc = (EncodeFn)fn;
  CUtensorMap mx, mw, mo, mu, mout, mut;
  const cuuint32_t es[5] = {1, 1, 1, 1, 1};
  {
    cuuint64_t dims[2] = {512, 2048}, st[1] = {1024};
    cuuint32_t box[2] = {64, 128};
    enc(&mx, CU_TENSOR_MAP_DATA_TYPE_BFLOAT16, 2, d_in[0], dims, st, box, es, CU_TENSOR_MAP_INTERLEAVE_NONE,
        CU_TENSOR_MAP_SWIZZLE_128B, CU_TENSOR_MAP_L2_PROMOTION_L2_128B, CU_TENSOR_MAP_FLOAT_OOB_FILL_NONE);
  }
  {
    cuuint64_t dims[3] = {512, 512, 3}, st[2] = {3072, 1024};
    cuuint32_t box[3] = {32, 64, 3};
    enc(&mw, CU_TENSOR_MAP_DATA_TYPE_BFLOAT16, 3, d_in[1], dims, st, box, es, CU_TENSOR_MAP_INTERLEAVE_NONE,
        CU_TENSOR_MAP_SWIZZLE_64B, CU_TENSOR_MAP_L2_PROMOTION_L2_128B, CU_TENSOR_MAP_FLOAT_OOB_FILL_NONE);
  }
  {
    cuuint64_t dims[3] = {64, 512, 8}, st[2] = {1024, 128};
    cuuint32_t box[3] = {64, 64, 2};
    enc(&mo, CU_TENSOR_MAP_DATA_TYPE_BFLOAT16, 3, d_in[3], dims, st, box, es, CU_TENSOR_MAP_INTERLEAVE_NONE,
        CU_TENSOR_MAP_SWIZZLE_128B, CU_TENSOR_MAP_L2_PROMOTION_L2_128B, CU_TENSOR_MAP_FLOAT_OOB_FILL_NONE);
  }
  {
    cuuint64_t dims[4] = {512, 4, 16, 32}, st[3] = {16384, 1024, 65536};
    cuuint32_t box[4] = {64, 4, 16, 2};
    enc(&mu, CU_TENSOR_MAP_DATA_TYPE_BFLOAT16, 4, d_in[4], dims, st, box, es, CU_TENSOR_MAP_INTERLEAVE_NONE,
        CU_TENSOR_MAP_SWIZZLE_128B, CU_TENSOR_MAP_L2_PROMOTION_L2_128B, CU_TENSOR_MAP_FLOAT_OOB_FILL_NONE);
  }
  {
    cuuint64_t dims[2] = {1024, 2048}, st[1] = {2048};
    cuuint32_t box[2] = {64, 16};
    enc(&mout, CU_TENSOR_MAP_DATA_TYPE_BFLOAT16, 2, d_out, dims, st, box, es, CU_TENSOR_MAP_INTERLEAVE_NONE,
        CU_TENSOR_MAP_SWIZZLE_128B, CU_TENSOR_MAP_L2_PROMOTION_NONE, CU_TENSOR_MAP_FLOAT_OOB_FILL_NONE);
  }
  Params P;
  P.x = (const __nv_bfloat16*)d_in[0];
  P.wphi = (const __nv_bfloat16*)d_in[2];
  P.wo = (const __nv_bfloat16*)d_in[3];
  P.logA = (const __nv_bfloat16*)d_in[5];
  P.Aim = (const __nv_bfloat16*)d_in[6];
  P.Cre = (const __nv_bfloat16*)d_in[7];
  P.Cim = (const __nv_bfloat16*)d_in[8];
  P.logdt = (const __nv_bfloat16*)d_in[9];
  P.Dskip = (const __nv_bfloat16*)d_in[10];
  P.out = (__nv_bfloat16*)d_out;
  cudaGetSymbolAddress((void**)&P.xs, g_x);
  {
    cuuint64_t dims[3] = {1024, 2, 512}, st[2] = {U_ODD, U_CH};
    cuuint32_t box[3] = {64, 2, 64};
    enc(&mut, CU_TENSOR_MAP_DATA_TYPE_BFLOAT16, 3, P.xs + X_UT + U_PAD / 16, dims, st, box, es, CU_TENSOR_MAP_INTERLEAVE_NONE,
        CU_TENSOR_MAP_SWIZZLE_128B, CU_TENSOR_MAP_L2_PROMOTION_NONE, CU_TENSOR_MAP_FLOAT_OOB_FILL_NONE);
  }
  P.ts = nullptr;
  cudaFuncSetAttribute(fused_kernel, cudaFuncAttributeMaxDynamicSharedMemorySize, SMEM_BYTES);
  fused_kernel<<<NCTA, NTHREADS, SMEM_BYTES>>>(P, mx, mw, mo, mu, mout, mut);
}
```

```cpp
#include <cuda_runtime.h>
#include <cuda_bf16.h>
#include <cuda_fp16.h>
#include <cuda.h>
#include <stdint.h>
#include <type_traits>

#define DBG_TS 0

namespace {

constexpr int NTHREADS = 512;
constexpr int NCTA = 128;
constexpr int OFF_W = 0;
constexpr int OFF_X = 98304;
constexpr int OFF_U = OFF_X + 65536;
constexpr int U_CH = 4416, U_ODD = 2240, U_PAD = 128;
constexpr int OFF_STG0 = OFF_U + 18432;
constexpr int SLAB = 3328;
constexpr int OFF_T = OFF_STG0 + 8 * SLAB;
constexpr int T_CH = 5216;
constexpr int T_D = 0;
constexpr int T_5 = 2144;
constexpr int T_3 = T_5 + 384;
constexpr int T_7 = T_5 + 1024;
constexpr int T_9 = T_7 + 320;
constexpr int T_KC = T_9 + 320;
constexpr int T_ST = T_5 - 1024;
constexpr int OFF_PHI = OFF_T + 4 * T_CH;
constexpr int OFF_EYE = OFF_PHI + 1024, OFF_ONE = OFF_EYE + 512;
constexpr int OFF_BAR = OFF_ONE + 256;
constexpr int SMEM_BYTES = OFF_BAR + 512 + 256 * DBG_TS;
constexpr uint32_t SB = 1024;
static_assert(T_KC + 2 * 656 <= T_CH, "table size");
static_assert(SMEM_BYTES <= 232448, "smem");
constexpr int MB_URAW = 0, MB_FULL = 1  , MB_WO = 17, MB_UFULL = 18, MB_O = 19  ,
              MB_EMPTY = 23  , MB_AUX = 39;
__host__ __device__ constexpr uint32_t BAR(int i) { return SB + OFF_BAR + 8 * i; }
constexpr int NB_WG0 = 1, NB_ODONE = 2, NB_ST0 = 3, NB_HAND = 4, NB_KV = 5, NB_YZ = 6, NB_INIT = 7, NB_PREP = 8, NB_PROD = 9, NB_KREAD = 10,
              NB_BDONE = 11, NB_GATE = 12  , NB_Y = 7  ;
#define STORE_AT 2
#define UAT 2
constexpr int U_AT = UAT;
constexpr int ZERO_STEP = 12;
constexpr int SPIN_MAX = 1 << 16;

constexpr int X_CNT = 0;
constexpr int X_PART = 256;
constexpr int X_O = X_PART + 16 * 8 * 144;
constexpr int X_Y = X_O + 32 * 32 * 128;
constexpr int X_UT = X_Y + 512 * 8 * 32;
constexpr int X_SIZE = X_UT + 512 * (U_CH / 16);
__device__ __align__(128) uint4 g_x[X_SIZE];
extern __shared__ uint8_t smem_raw[];
#define TS(i) do {} while (0)
#define TS1(i) do {} while (0)
#define GT(i) do {} while (0)
#define TSDUMP(base) do {} while (0)

__device__ __forceinline__ uint32_t smem_u32(const void* p) { return (uint32_t)__cvta_generic_to_shared(p); }
__device__ __forceinline__ void mbar_arrive(uint32_t b) {
  asm volatile("mbarrier.arrive.shared::cta.b64 _, [%0];" ::"r"(b) : "memory");
}
__device__ __forceinline__ void mbar_wait(uint32_t b) {
  uint32_t done = 0;
#pragma unroll 1
  for (int i = 0; i < SPIN_MAX && !done; i++) {
    asm volatile("{\n.reg .pred p;\nmbarrier.try_wait.parity.shared::cta.b64 p, [%1], 0, 4000;\nselp.u32 %0, 1, 0, p;\n}\n"
                 : "=r"(done) : "r"(b) : "memory");
  }
}
__device__ __forceinline__ void mbar_spin(uint32_t b) {
  uint32_t done = 0;
#pragma unroll 1
  for (int i = 0; i < (SPIN_MAX << 4) && !done; i++) {
    asm volatile("{\n.reg .pred p;\nmbarrier.try_wait.parity.shared::cta.b64 p, [%1], 0;\nselp.u32 %0, 1, 0, p;\n}\n"
                 : "=r"(done) : "r"(b) : "memory");
  }
}
__device__ __forceinline__ void mbar_init(uint32_t b, int n) {
  asm volatile("mbarrier.init.shared::cta.b64 [%0], %1;" ::"r"(b), "r"(n) : "memory");
}
__device__ __forceinline__ void mbar_expect(uint32_t b, int bytes) {
  asm volatile("mbarrier.arrive.expect_tx.shared::cta.b64 _, [%0], %1;" ::"r"(b), "r"(bytes) : "memory");
}
__device__ __forceinline__ void nb_sync(int id, int n) { asm volatile("bar.sync %0, %1;" ::"r"(id), "r"(n) : "memory"); }
__device__ __forceinline__ void nb_arrive(int id, int n) { asm volatile("bar.arrive %0, %1;" ::"r"(id), "r"(n) : "memory"); }
#define ELECT "{\n.reg .pred p;\nelect.sync _|p, 0xffffffff;\n@p "
__device__ __forceinline__ void e_arrive(uint32_t b) {
  asm volatile(ELECT "mbarrier.arrive.shared::cta.b64 _, [%0];\n}\n" ::"r"(b) : "memory");
}
__device__ __forceinline__ void e_expect(uint32_t b, int bytes) {
  asm volatile(ELECT "mbarrier.arrive.expect_tx.shared::cta.b64 _, [%0], %1;\n}\n" ::"r"(b), "r"(bytes) : "memory");
}
__device__ __forceinline__ void e_tma2d(uint32_t dst, const CUtensorMap* m, uint32_t bar, int c0, int c1) {
  asm volatile(ELECT "cp.async.bulk.tensor.2d.shared::cluster.global.mbarrier::complete_tx::bytes [%0], [%1, {%3,%4}], [%2];\n}\n"
               ::"r"(dst), "l"(m), "r"(bar), "r"(c0), "r"(c1) : "memory");
}
__device__ __forceinline__ void e_tma3d(uint32_t dst, const CUtensorMap* m, uint32_t bar, int c0, int c1, int c2) {
  asm volatile(ELECT "cp.async.bulk.tensor.3d.shared::cluster.global.mbarrier::complete_tx::bytes [%0], [%1, {%3,%4,%5}], [%2];\n}\n"
               ::"r"(dst), "l"(m), "r"(bar), "r"(c0), "r"(c1), "r"(c2) : "memory");
}
__device__ __forceinline__ void e_tma4d(uint32_t dst, const CUtensorMap* m, uint32_t bar, int c0, int c3) {
  asm volatile(ELECT "cp.async.bulk.tensor.4d.shared::cluster.global.mbarrier::complete_tx::bytes [%0], [%1, {%3,%5,%5,%4}], [%2];\n}\n"
               ::"r"(dst), "l"(m), "r"(bar), "r"(c0), "r"(c3), "r"(0) : "memory");
}
__device__ __forceinline__ void e_bulk(uint32_t dst, const void* src, int bytes, uint32_t bar) {
  asm volatile(ELECT "cp.async.bulk.shared::cluster.global.mbarrier::complete_tx::bytes [%0], [%1], %2, [%3];\n}\n"
               ::"r"(dst), "l"(src), "r"(bytes), "r"(bar) : "memory");
}
__device__ __forceinline__ void e_prefetch(const void* p, int bytes) {
  asm volatile(ELECT "cp.async.bulk.prefetch.L2.global [%0], %1;\n}\n" ::"l"(p), "r"(bytes) : "memory");
}
__device__ __forceinline__ void e_store2d(const CUtensorMap* m, uint32_t src, int c0, int c1) {
  asm volatile(ELECT "cp.async.bulk.tensor.2d.global.shared::cta.bulk_group [%0, {%2,%3}], [%1];\n}\n"
               ::"l"(m), "r"(src), "r"(c0), "r"(c1) : "memory");
}
__host__ __device__ constexpr uint64_t mkdesc(uint32_t addr, uint32_t lbo, uint32_t sbo, int swz) {
  return (uint64_t)((addr & 0x3FFFF) >> 4) | ((uint64_t)(lbo >> 4) << 16) | ((uint64_t)(sbo >> 4) << 32) |
         ((uint64_t)swz << 62);
}
#define SPLIT() asm volatile("{\n.reg .pred p;\nsetp.eq.u32 p, %0, %1;\n@p exit;\n}\n" ::"r"(blockIdx.y), "n"(__LINE__) : "memory")
#define SPLITN(n) asm volatile("{\n.reg .pred p;\nsetp.eq.u32 p, %0, %1;\n@p exit;\n}\n" ::"r"(blockIdx.y), "r"(4096 + (n)) : "memory")
#define WG_FENCE() asm volatile("wgmma.fence.sync.aligned;" ::: "memory")
#define WG_COMMIT() asm volatile("wgmma.commit_group.sync.aligned;" ::: "memory")
#define WG_WAIT(n) asm volatile("wgmma.wait_group.sync.aligned " #n ";" ::: "memory")

__device__ __forceinline__ void mma(float& d0, float& d1, float& d2, float& d3, uint32_t a0, uint32_t a1, uint32_t a2,
                                    uint32_t a3, uint32_t b0, uint32_t b1) {
  asm volatile("mma.sync.aligned.m16n8k16.row.col.f32.bf16.bf16.f32 {%0,%1,%2,%3},{%4,%5,%6,%7},{%8,%9},{%0,%1,%2,%3};"
               : "+f"(d0), "+f"(d1), "+f"(d2), "+f"(d3)
               : "r"(a0), "r"(a1), "r"(a2), "r"(a3), "r"(b0), "r"(b1));
}
__device__ __forceinline__ void mmac(float (&d)[4], uint32_t a0, uint32_t a1, uint32_t a2, uint32_t a3, uint32_t b0,
                                     uint32_t b1, const float (&c)[4]) {
  asm volatile("mma.sync.aligned.m16n8k16.row.col.f32.bf16.bf16.f32 {%0,%1,%2,%3},{%4,%5,%6,%7},{%8,%9},{%10,%11,%12,%13};"
               : "=f"(d[0]), "=f"(d[1]), "=f"(d[2]), "=f"(d[3])
               : "r"(a0), "r"(a1), "r"(a2), "r"(a3), "r"(b0), "r"(b1), "f"(c[0]), "f"(c[1]), "f"(c[2]), "f"(c[3]));
}
__device__ __forceinline__ void mma_h(float (&d)[4], const uint32_t (&a)[4], uint32_t b0, uint32_t b1) {
  asm volatile("mma.sync.aligned.m16n8k16.row.col.f32.f16.f16.f32 {%0,%1,%2,%3},{%4,%5,%6,%7},{%8,%9},{%0,%1,%2,%3};"
               : "+f"(d[0]), "+f"(d[1]), "+f"(d[2]), "+f"(d[3]) : "r"(a[0]), "r"(a[1]), "r"(a[2]), "r"(a[3]), "r"(b0), "r"(b1));
}
__device__ __forceinline__ void mma0(float& d0, float& d1, float& d2, float& d3, uint32_t a0, uint32_t a1, uint32_t a2,
                                     uint32_t a3, uint32_t b0, uint32_t b1) {
  asm volatile("mma.sync.aligned.m16n8k16.row.col.f32.bf16.bf16.f32 {%0,%1,%2,%3},{%4,%5,%6,%7},{%8,%9},{%10,%10,%10,%10};"
               : "=f"(d0), "=f"(d1), "=f"(d2), "=f"(d3)
               : "r"(a0), "r"(a1), "r"(a2), "r"(a3), "r"(b0), "r"(b1), "f"(0.f));
}
__device__ __forceinline__ uint32_t pack_bf(float lo, float hi) {
  uint32_t r;
  asm("cvt.rn.bf16x2.f32 %0, %1, %2;" : "=r"(r) : "f"(hi), "f"(lo));
  return r;
}
__device__ __forceinline__ float bf_lo(uint32_t w) { return __uint_as_float(w << 16); }
__device__ __forceinline__ float bf_hi(uint32_t w) { return __uint_as_float(w & 0xffff0000u); }
__device__ __forceinline__ float bf_round(float x) { return __bfloat162float(__float2bfloat16_rn(x)); }
__device__ __forceinline__ uint32_t bmax2(uint32_t a, uint32_t b) {
  uint32_t r; asm("max.bf16x2 %0, %1, %2;" : "=r"(r) : "r"(a), "r"(b)); return r;
}
__device__ __forceinline__ uint32_t bmin2(uint32_t a, uint32_t b) {
  uint32_t r; asm("min.bf16x2 %0, %1, %2;" : "=r"(r) : "r"(a), "r"(b)); return r;
}
__device__ __forceinline__ float ex2(float x) { float r; asm("ex2.approx.ftz.f32 %0, %1;" : "=f"(r) : "f"(x)); return r; }
__device__ __forceinline__ float rcp(float x) { float r; asm("rcp.approx.ftz.f32 %0, %1;" : "=f"(r) : "f"(x)); return r; }
__device__ __forceinline__ void ldsm4(uint32_t (&r)[4], uint32_t a) {
  asm volatile("ldmatrix.sync.aligned.m8n8.x4.shared.b16 {%0,%1,%2,%3}, [%4];"
               : "=r"(r[0]), "=r"(r[1]), "=r"(r[2]), "=r"(r[3]) : "r"(a) : "memory");
}
__device__ __forceinline__ void ldsm4t(uint32_t (&r)[4], uint32_t a) {
  asm volatile("ldmatrix.sync.aligned.m8n8.x4.trans.shared.b16 {%0,%1,%2,%3}, [%4];"
               : "=r"(r[0]), "=r"(r[1]), "=r"(r[2]), "=r"(r[3]) : "r"(a) : "memory");
}
__device__ __forceinline__ void stsm4(uint32_t a, uint32_t r0, uint32_t r1, uint32_t r2, uint32_t r3) {
  asm volatile("stmatrix.sync.aligned.m8n8.x4.shared.b16 [%0], {%1,%2,%3,%4};"
               ::"r"(a), "r"(r0), "r"(r1), "r"(r2), "r"(r3) : "memory");
}
__device__ __forceinline__ uint32_t lds32(uint32_t a) {
  uint32_t r; asm volatile("ld.shared.u32 %0, [%1];" : "=r"(r) : "r"(a) : "memory"); return r;
}
__device__ __forceinline__ uint32_t lds16(uint32_t a) {
  uint32_t r; asm volatile("{\n.reg .u16 h;\nld.shared.u16 h, [%1];\ncvt.u32.u16 %0, h;\n}\n" : "=r"(r) : "r"(a) : "memory"); return r;
}
__device__ __forceinline__ uint2 lds64(uint32_t a) {
  uint2 r; asm volatile("ld.shared.v2.u32 {%0,%1}, [%2];" : "=r"(r.x), "=r"(r.y) : "r"(a) : "memory"); return r;
}
__device__ __forceinline__ uint4 lds128(uint32_t a) {
  uint4 r;
  asm volatile("ld.shared.v4.u32 {%0,%1,%2,%3}, [%4];" : "=r"(r.x), "=r"(r.y), "=r"(r.z), "=r"(r.w) : "r"(a) : "memory");
  return r;
}
__device__ __forceinline__ void sts32(uint32_t a, uint32_t v) { asm volatile("st.shared.u32 [%0], %1;" ::"r"(a), "r"(v) : "memory"); }
__device__ __forceinline__ void sts16(uint32_t a, uint32_t v) {
  asm volatile("{\n.reg .u16 h;\ncvt.u16.u32 h, %1;\nst.shared.u16 [%0], h;\n}\n" ::"r"(a), "r"(v) : "memory");
}
__device__ __forceinline__ void sts64(uint32_t a, uint32_t x, uint32_t y) {
  asm volatile("st.shared.v2.u32 [%0], {%1,%2};" ::"r"(a), "r"(x), "r"(y) : "memory");
}
__device__ __forceinline__ void sts128(uint32_t a, uint32_t x, uint32_t y, uint32_t z, uint32_t w) {
  asm volatile("st.shared.v4.u32 [%0], {%1,%2,%3,%4};" ::"r"(a), "r"(x), "r"(y), "r"(z), "r"(w) : "memory");
}
__device__ __forceinline__ uint4 ld_x(const uint4* p) {
  uint4 r;
  asm volatile("{\n.reg .b128 t;\nld.relaxed.gpu.global.b128 t, [%4];\nmov.b128 {%0,%1,%2,%3}, t;\n}\n"
               : "=r"(r.x), "=r"(r.y), "=r"(r.z), "=r"(r.w) : "l"(p) : "memory");
  return r;
}
__device__ __forceinline__ uint32_t ld_x32(const uint32_t* p) {
  uint32_t r; asm volatile("ld.relaxed.gpu.global.u32 %0, [%1];" : "=r"(r) : "l"(p) : "memory"); return r;
}
__device__ __forceinline__ void st_x(uint4* p, uint32_t x, uint32_t y, uint32_t z, uint32_t w) {
  asm volatile("{\n.reg .b128 t;\nmov.b128 t, {%1,%2,%3,%4};\nst.relaxed.gpu.global.b128 [%0], t;\n}\n"
               ::"l"(p), "r"(x), "r"(y), "r"(z), "r"(w) : "memory");
}
__device__ __forceinline__ void st_x32(uint32_t* p, uint32_t x) {
  asm volatile("st.relaxed.gpu.global.u32 [%0], %1;" ::"l"(p), "r"(x) : "memory");
}
__device__ __forceinline__ uint32_t nz(uint32_t w) { return max(w, 1u); }
__device__ __forceinline__ uint32_t fu(float x) { return __float_as_uint(x); }
__device__ __forceinline__ float uf(uint32_t x) { return __uint_as_float(x); }

__device__ __forceinline__ void wgmma_ss_n96(float (&d)[48], uint64_t da, uint64_t db, int sc) {
  asm volatile("{\n.reg .pred p;\nsetp.ne.b32 p, %50, 0;\n"
      "wgmma.mma_async.sync.aligned.m64n96k16.f32.bf16.bf16 "
      "{%0,%1,%2,%3,%4,%5,%6,%7,%8,%9,%10,%11,%12,%13,%14,%15,%16,%17,%18,%19,%20,%21,%22,%23,%24,%25,%26,%27,%28,%29,%30,%31,%32,%33,%34,%35,%36,%37,%38,%39,%40,%41,%42,%43,%44,%45,%46,%47}, "
      "%48, %49, p, 1, 1, 0, 1;\n}\n"
      : "+f"(d[0]), "+f"(d[1]), "+f"(d[2]), "+f"(d[3]), "+f"(d[4]), "+f"(d[5]), "+f"(d[6]), "+f"(d[7]),
        "+f"(d[8]), "+f"(d[9]), "+f"(d[10]), "+f"(d[11]), "+f"(d[12]), "+f"(d[13]), "+f"(d[14]), "+f"(d[15]),
        "+f"(d[16]), "+f"(d[17]), "+f"(d[18]), "+f"(d[19]), "+f"(d[20]), "+f"(d[21]), "+f"(d[22]), "+f"(d[23]),
        "+f"(d[24]), "+f"(d[25]), "+f"(d[26]), "+f"(d[27]), "+f"(d[28]), "+f"(d[29]), "+f"(d[30]), "+f"(d[31]),
        "+f"(d[32]), "+f"(d[33]), "+f"(d[34]), "+f"(d[35]), "+f"(d[36]), "+f"(d[37]), "+f"(d[38]), "+f"(d[39]),
        "+f"(d[40]), "+f"(d[41]), "+f"(d[42]), "+f"(d[43]), "+f"(d[44]), "+f"(d[45]), "+f"(d[46]), "+f"(d[47])
      : "l"(da), "l"(db), "r"(sc));
}

__device__ __forceinline__ void wgmma_ss_n128(float (&d)[64], uint64_t da, uint64_t db, int sc) {
  asm volatile("{\n.reg .pred p;\nsetp.ne.b32 p, %66, 0;\n"
      "wgmma.mma_async.sync.aligned.m64n128k16.f32.bf16.bf16 "
      "{%0,%1,%2,%3,%4,%5,%6,%7,%8,%9,%10,%11,%12,%13,%14,%15,%16,%17,%18,%19,%20,%21,%22,%23,%24,%25,%26,%27,%28,%29,%30,%31,%32,%33,%34,%35,%36,%37,%38,%39,%40,%41,%42,%43,%44,%45,%46,%47,%48,%49,%50,%51,%52,%53,%54,%55,%56,%57,%58,%59,%60,%61,%62,%63}, "
      "%64, %65, p, 1, 1, 0, 1;\n}\n"
      : "+f"(d[0]), "+f"(d[1]), "+f"(d[2]), "+f"(d[3]), "+f"(d[4]), "+f"(d[5]), "+f"(d[6]), "+f"(d[7]),
        "+f"(d[8]), "+f"(d[9]), "+f"(d[10]), "+f"(d[11]), "+f"(d[12]), "+f"(d[13]), "+f"(d[14]), "+f"(d[15]),
        "+f"(d[16]), "+f"(d[17]), "+f"(d[18]), "+f"(d[19]), "+f"(d[20]), "+f"(d[21]), "+f"(d[22]), "+f"(d[23]),
        "+f"(d[24]), "+f"(d[25]), "+f"(d[26]), "+f"(d[27]), "+f"(d[28]), "+f"(d[29]), "+f"(d[30]), "+f"(d[31]),
        "+f"(d[32]), "+f"(d[33]), "+f"(d[34]), "+f"(d[35]), "+f"(d[36]), "+f"(d[37]), "+f"(d[38]), "+f"(d[39]),
        "+f"(d[40]), "+f"(d[41]), "+f"(d[42]), "+f"(d[43]), "+f"(d[44]), "+f"(d[45]), "+f"(d[46]), "+f"(d[47]),
        "+f"(d[48]), "+f"(d[49]), "+f"(d[50]), "+f"(d[51]), "+f"(d[52]), "+f"(d[53]), "+f"(d[54]), "+f"(d[55]),
        "+f"(d[56]), "+f"(d[57]), "+f"(d[58]), "+f"(d[59]), "+f"(d[60]), "+f"(d[61]), "+f"(d[62]), "+f"(d[63])
      : "l"(da), "l"(db), "r"(sc));
}

__device__ __forceinline__ void wgmma_ss_n40(float (&d)[20], uint64_t da, uint64_t db, int sc) {
  asm volatile("{\n.reg .pred p;\nsetp.ne.b32 p, %22, 0;\n"
      "wgmma.mma_async.sync.aligned.m64n40k16.f32.bf16.bf16 "
      "{%0,%1,%2,%3,%4,%5,%6,%7,%8,%9,%10,%11,%12,%13,%14,%15,%16,%17,%18,%19}, "
      "%20, %21, p, 1, 1, 1, 1;\n}\n"
      : "+f"(d[0]), "+f"(d[1]), "+f"(d[2]), "+f"(d[3]), "+f"(d[4]), "+f"(d[5]), "+f"(d[6]), "+f"(d[7]),
        "+f"(d[8]), "+f"(d[9]), "+f"(d[10]), "+f"(d[11]), "+f"(d[12]), "+f"(d[13]), "+f"(d[14]), "+f"(d[15]),
        "+f"(d[16]), "+f"(d[17]), "+f"(d[18]), "+f"(d[19])
      : "l"(da), "l"(db), "r"(sc));
}

__device__ __forceinline__ void wgmma_rs_n8(float (&d)[4], const uint4& a, uint64_t db, int sc) {
  asm volatile("{\n.reg .pred p;\nsetp.ne.b32 p, %9, 0;\n"
      "wgmma.mma_async.sync.aligned.m64n8k16.f32.bf16.bf16 "
      "{%0,%1,%2,%3}, "
      "{%4,%5,%6,%7}, %8, p, 1, 1, 1;\n}\n"
      : "+f"(d[0]), "+f"(d[1]), "+f"(d[2]), "+f"(d[3])
      : "r"(a.x), "r"(a.y), "r"(a.z), "r"(a.w), "l"(db), "r"(sc));
}

__device__ __forceinline__ void wgmma_rs_n16(float (&d)[8], const uint4& a, uint64_t db, int sc) {
  asm volatile("{\n.reg .pred p;\nsetp.ne.b32 p, %13, 0;\n"
      "wgmma.mma_async.sync.aligned.m64n16k16.f32.bf16.bf16 "
      "{%0,%1,%2,%3,%4,%5,%6,%7}, "
      "{%8,%9,%10,%11}, %12, p, 1, 1, 1;\n}\n"
      : "+f"(d[0]), "+f"(d[1]), "+f"(d[2]), "+f"(d[3]), "+f"(d[4]), "+f"(d[5]), "+f"(d[6]), "+f"(d[7])
      : "r"(a.x), "r"(a.y), "r"(a.z), "r"(a.w), "l"(db), "r"(sc));
}

__device__ __forceinline__ void wgmma_rs_n24(float (&d)[12], const uint4& a, uint64_t db, int sc) {
  asm volatile("{\n.reg .pred p;\nsetp.ne.b32 p, %17, 0;\n"
      "wgmma.mma_async.sync.aligned.m64n24k16.f32.bf16.bf16 "
      "{%0,%1,%2,%3,%4,%5,%6,%7,%8,%9,%10,%11}, "
      "{%12,%13,%14,%15}, %16, p, 1, 1, 1;\n}\n"
      : "+f"(d[0]), "+f"(d[1]), "+f"(d[2]), "+f"(d[3]), "+f"(d[4]), "+f"(d[5]), "+f"(d[6]), "+f"(d[7]),
        "+f"(d[8]), "+f"(d[9]), "+f"(d[10]), "+f"(d[11])
      : "r"(a.x), "r"(a.y), "r"(a.z), "r"(a.w), "l"(db), "r"(sc));
}

struct Params {
  const __nv_bfloat16 *logA, *Aim, *Cre, *Cim, *logdt, *Dskip, *x, *wphi, *wo;
  __nv_bfloat16* out;
  uint4* xs;
  long long* ts;
};

__device__ __forceinline__ uint4 tr_row(const uint4 (&v)[8], int i) {
  uint32_t o[4];
#pragma unroll
  for (int m = 0; m < 4; m++) {
    const uint4 &ra = v[2 * m], &rb = v[2 * m + 1];
    const int k = i >> 1;
    const uint32_t xa = k == 0 ? ra.x : k == 1 ? ra.y : k == 2 ? ra.z : ra.w;
    const uint32_t xb = k == 0 ? rb.x : k == 1 ? rb.y : k == 2 ? rb.z : rb.w;
    o[m] = __byte_perm(xa, xb, (i & 1) ? 0x7632 : 0x5410);
  }
  return make_uint4(o[0], o[1], o[2], o[3]);
}

struct cpx { float r, i; };
__device__ __forceinline__ cpx csq(cpx a) { return {a.r * a.r - a.i * a.i, 2.f * (a.r * a.i)}; }
__device__ __forceinline__ cpx polar(float e, float t) {
  const float m = ex2(e);
  return {m * __cosf(t), m * __sinf(t)};
}

struct KgenRaw { uint32_t la, ai, cr, ci, ldt; };
__device__ __forceinline__ KgenRaw kgen_load(const Params& P, int d, int unit, int lane, int on) {
  const int o = d * 64 + unit * 32 + lane;
  KgenRaw r = {0, 0, 0, 0, 0};
  asm volatile("{\n.reg .pred p;\nsetp.ne.b32 p, %10, 0;\n@p ld.global.nc.u32 %0, [%5];\n@p ld.global.nc.u32 %1, [%6];\n"
               "@p ld.global.nc.u32 %2, [%7];\n@p ld.global.nc.u32 %3, [%8];\n@p ld.global.nc.u16 %4, [%9];\n}\n"
               : "+r"(r.la), "+r"(r.ai), "+r"(r.cr), "+r"(r.ci), "+r"(r.ldt)
               : "l"((const uint32_t*)P.logA + o), "l"((const uint32_t*)P.Aim + o), "l"((const uint32_t*)P.Cre + o),
                 "l"((const uint32_t*)P.Cim + o), "l"(P.logdt + d), "r"(on));
  return r;
}
struct hc { __half2 r, i; };
struct cpx2 { cpx a, b; };
__device__ __forceinline__ cpx2 csq2(const cpx2& v) { return {csq(v.a), csq(v.b)}; }
__device__ __forceinline__ hc toh(const cpx2& v) { return {__floats2half2_rn(v.a.r, v.b.r), __floats2half2_rn(v.a.i, v.b.i)}; }
__device__ __forceinline__ hc hmul(const hc& z, const hc& w) {
  return {__hfma2(z.r, w.r, __hneg2(__hmul2(z.i, w.i))), __hfma2(z.r, w.i, __hmul2(z.i, w.r))};
}
__device__ __forceinline__ hc hmulc(const hc& z, const hc& w) {
  return {__hfma2(z.r, w.r, __hmul2(z.i, w.i)), __hfma2(z.i, w.r, __hneg2(__hmul2(z.r, w.i)))};
}
__device__ __forceinline__ uint32_t hu(__half2 v) { return *(const uint32_t*)&v; }
__device__ __forceinline__ __half2 uh(uint32_t v) { return *(const __half2*)&v; }

struct KgenAddr { uint32_t sa[2], ld[5][4]; };
__device__ __forceinline__ KgenAddr kgen_addr(int lane, uint32_t buf) {
  KgenAddr a;
  a.sa[0] = buf + (lane & 7) * 128 + ((((lane >> 3) ^ lane) & 7) << 4);
  a.sa[1] = a.sa[0] ^ 64;
  const int q = lane >> 4;
  const uint32_t b = buf + ((lane >> 3) & 1) * 1024 + q * 128;
  const int e[5] = {lane & 7, 0, 1, 2 + (lane & 1), 4 + (lane & 3)};
#pragma unroll
  for (int i = 0; i < 20; i++) {
    a.ld[i >> 2][i & 3] = b + ((e[i >> 2] ^ q ^ (2 * (i & 3))) << 4);
    asm volatile("" : "+r"(a.ld[i >> 2][i & 3]));
  }
  asm volatile("" : "+r"(a.sa[0]), "+r"(a.sa[1]));
  return a;
}
__device__ __forceinline__ void kgen_unit(const KgenRaw& r, const KgenAddr& ad, uint32_t zero, float (&k)[5][4], float& k2048, float& sc) {
  const float dt = bf_round(expf(bf_lo(r.ldt)));
  const uint32_t ar = pack_bf(ex2(bf_lo(r.la) * 1.4426950408889634f), ex2(bf_hi(r.la) * 1.4426950408889634f));
  const float ca = dt * -1.4426950408889634f, a0 = bf_lo(ar) * ca, a1 = bf_hi(ar) * ca;
  const float f0 = bf_lo(r.ai) * dt, f1 = bf_hi(r.ai) * dt;
  const float r0 = f0 * 20.21267777267071f, r1 = f1 * 20.21267777267071f;
  const uint32_t cm = __vmaxu2(r.cr & 0x7fff7fffu, r.ci & 0x7fff7fffu);
  const uint32_t ex = min(max(__reduce_max_sync(0xffffffffu, max(cm >> 16, cm & 0xffffu)) >> 7, 1u), 253u);
  const float cs = uf((254u - ex) << 23);
  sc = 2.f * dt * uf(ex << 23);
  const cpx2 C = {{bf_lo(r.cr) * cs, bf_lo(r.ci) * -cs}, {bf_hi(r.cr) * cs, bf_hi(r.ci) * -cs}};
  auto put = [&](const hc (&v)[8]) {
    stsm4(ad.sa[0], hu(v[0].r), hu(v[1].r), hu(v[2].r), hu(v[3].r));
    stsm4(ad.sa[0] + 1024, hu(v[0].i), hu(v[1].i), hu(v[2].i), hu(v[3].i));
    stsm4(ad.sa[1], hu(v[4].r), hu(v[5].r), hu(v[6].r), hu(v[7].r));
    stsm4(ad.sa[1] + 1024, hu(v[4].i), hu(v[5].i), hu(v[6].i), hu(v[7].i));
    __syncwarp();
  };
  auto get = [&](uint32_t (&o)[4][4], const uint32_t (&a)[4]) {
#pragma unroll
    for (int i = 0; i < 4; i++) ldsm4(o[i], a[i] + i * 256);
  };
  auto at = [](const uint32_t (&o)[4][4], int s) { return hc{uh(o[s >> 1][2 * (s & 1)]), uh(o[s >> 1][2 * (s & 1) + 1])}; };
  uint32_t A[8][4];
  auto tile = [&](int j, const uint32_t (&B)[4][4]) {
    k[j][0] = k[j][1] = k[j][2] = k[j][3] = 0.f;
#pragma unroll
    for (int s = 0; s < 8; s++) mma_h(k[j], A[s], B[s >> 1][2 * (s & 1)], B[s >> 1][2 * (s & 1) + 1]);
  };
  const cpx2 w1 = {polar(a0, f0), polar(a1, f1)};
  const cpx2 w127 = {polar(a0 * 127.f, (r0 - rintf(r0)) * 6.283185307179586f), polar(a1 * 127.f, (r1 - rintf(r1)) * 6.283185307179586f)};
  const cpx2 w2 = csq2(w1), w4 = csq2(w2);
  uint32_t T0[4][4], X[4][4], M[3][4][4];
  {
    hc t[8];
    t[0] = {uh(0x3C003C00u), uh(0u)}; t[1] = toh(w1); t[2] = toh(w2); t[4] = toh(w4);
    t[3] = hmul(t[1], t[2]); t[5] = hmul(t[1], t[4]); t[6] = hmul(t[2], t[4]); t[7] = hmul(t[3], t[4]);
    put(t); get(T0, ad.ld[0]);
  }
  SPLIT();
  const cpx2 w8 = csq2(w4), w16 = csq2(w8), w32 = csq2(w16), w64 = csq2(w32);
  {
    const hc m8 = toh(w8), m16 = toh(w16), m32 = toh(w32);
    hc a[8];
    a[0] = toh(C); a[1] = hmulc(a[0], m8);
    a[2] = hmulc(a[0], m16); a[3] = hmulc(a[1], m16);
#pragma unroll
    for (int i = 0; i < 4; i++) a[4 + i] = hmulc(a[i], m32);
    put(a); get(X, ad.ld[0]);
  }
  SPLIT();
    const cpx2 w128 = {{w127.a.r * w1.a.r - w127.a.i * w1.a.i, w127.a.r * w1.a.i + w127.a.i * w1.a.r},
                     {w127.b.r * w1.b.r - w127.b.i * w1.b.i, w127.b.r * w1.b.i + w127.b.i * w1.b.r}};
  const cpx2 w256 = csq2(w128), w512 = csq2(w256);
  const hc m128 = toh(w128), m256 = toh(w256), m512 = toh(w512);
  {
    const hc m254 = toh(csq2(w127)), m127 = toh(w127);
    hc m[8];
    m[0] = toh(w64); m[1] = m128; m[2] = m256; m[3] = hmul(m127, m256);
    m[4] = m512; m[5] = hmul(m127, m512); m[6] = hmul(m[4], m254); m[7] = hmul(m[5], m254);
    put(m);
    get(M[0], ad.ld[1]);
#pragma unroll
    for (int s = 0; s < 8; s++) {
      const hc z = at(X, s), y = hmulc(z, at(M[0], s));
      A[s][0] = hu(z.r) + zero; A[s][1] = hu(y.r); A[s][2] = hu(z.i) + zero; A[s][3] = hu(y.i);
    }
#pragma unroll
    for (int i = 0; i < 3; i++) get(M[i], ad.ld[i + 2]);
  }
  SPLIT();
  tile(0, T0);
  const cpx2 w1024 = csq2(w512), we = csq2(w1024);
  {
    hc t[8];
    t[0] = toh(w1024); t[1] = hmul(t[0], m128);
    t[2] = hmul(t[0], m256); t[3] = hmul(t[1], m256);
#pragma unroll
    for (int i = 0; i < 4; i++) t[4 + i] = hmul(t[i], m512);
    put(t); get(X, ad.ld[0]);
  }
  k2048 = (C.a.r * we.a.r + C.a.i * we.a.i + C.b.r * we.b.r + C.b.i * we.b.i) * sc;
#pragma unroll
  for (int j = 1; j < 5; j++) k[j][0] = k[j][1] = k[j][2] = k[j][3] = 0.f;
#pragma unroll
  for (int s = 0; s < 8; s++) {
#pragma unroll
    for (int j = 0; j < 3; j++) {
      const hc y = hmul(at(T0, s), at(M[j], s));
      mma_h(k[1 + j], A[s], hu(y.r), hu(y.i));
    }
    mma_h(k[4], A[s], X[s >> 1][2 * (s & 1)], X[s >> 1][2 * (s & 1) + 1]);
  }
}

__device__ __forceinline__ void build_tables(uint32_t tb, int lane, float (&k)[5][4], float k2048) {
  const int g = lane >> 2, c = lane & 3;
  const uint32_t kc = tb + T_KC + 16;
  {
    const uint32_t a0 = kc + 16 * g + 4 * c, a2 = kc + 2 * (256 + 4 * g + c);
    const uint32_t a3 = kc + 2 * (384 + 2 * g + 64 * (c & 1) + (c >> 1)), a4 = kc + 2 * (512 + g + 32 * c);
#pragma unroll
    for (int r = 0; r < 2; r++) {
      sts32(a0 + 128 * r, pack_bf(k[0][2 * r], k[0][2 * r + 1]));
      sts32(a0 + 128 * r + 256, pack_bf(k[1][2 * r], k[1][2 * r + 1]));
      const uint32_t w2 = pack_bf(k[2][2 * r], k[2][2 * r + 1]);
      const uint32_t w3 = pack_bf(k[3][2 * r], k[3][2 * r + 1]);
      const uint32_t w4 = pack_bf(k[4][2 * r], k[4][2 * r + 1]);
      sts16(a2 + 64 * r, w2); sts16(a2 + 64 * r + 128, w2 >> 16);
      sts16(a3 + 32 * r, w3); sts16(a3 + 32 * r + 64, w3 >> 16);
      sts16(a4 + 16 * r, w4); sts16(a4 + 16 * r + 32, w4 >> 16);
    }
  }
  if (lane == 0) { sts16(kc + 2 * 640, pack_bf(k2048, 0.f)); sts32(kc - 4, 0); }
  __syncwarp();
  const uint32_t td = tb + T_D + 32;
#pragma unroll
  for (int hf = 0; hf < 2; hf++) {
    const uint2 v = lds64(kc + 256 * hf + 8 * lane);
    const uint32_t pv = lds32(kc + 256 * hf + 8 * lane - 4);
    sts128(td + 512 * hf + 16 * lane, __byte_perm(v.x, pv, 0x7610), __byte_perm(v.x, v.x, 0x1032), __byte_perm(v.y, v.x, 0x7610),
           __byte_perm(v.y, v.y, 0x1032));
  }
#pragma unroll
  for (int hf = 0; hf < 2; hf++) {
    const uint32_t v = lds32(kc + 512 + 128 * hf + 4 * lane), nx = lds32(kc + 516 + 128 * hf + 4 * lane);
    uint32_t w0 = __byte_perm(v, v, 0x1010);
    const uint32_t w1 = w0;
    if (hf == 0) { const uint32_t pv = lds32(kc + 508); if (lane == 0) w0 = __byte_perm(v, pv, 0x7610); }
    sts128(td + 1024 + 512 * hf + 16 * lane, w0, w1, __byte_perm(v, v, 0x1032), __byte_perm(nx, v, 0x7610));
  }
  {
    const uint32_t kk = lds16(kc + 2 * 384);
    const uint32_t w = lane < 3 ? (kk | (kk << 16)) : (lane == 3 ? (kk << 16) : 0u);
    if (lane < 24) sts32(td + 4 * (lane < 16 ? 512 + lane : lane - 24), w);
    const uint32_t lo_ = lds16(kc + 2 * 511), le_ = lds16(kc + 2 * 512);
    const uint32_t ja = tb + T_5 + (lane < 16 ? 4 * lane : 256 + 4 * lane);
    sts32(ja, lane == 16 ? (le_ << 16) : 0u);
    sts32(ja + 384, lane == 16 ? (lo_ << 16) : 0u);
    sts32(tb + (lane < 16 ? T_7 : T_9 - 64) + 4 * lane, 0u);
  }
#pragma unroll
  for (int s = 0; s < 2; s++) {
    const uint32_t b = kc + 2 * (s ? 512 : 384) + 8 * lane;
    const uint2 v = lds64(b);
    uint32_t em = lds16(b - 2), e0 = v.x;
    const uint32_t e4 = lds16(b + 8);
    if (lane == 0) { em = 0; e0 = 0; }
    sts64(tb + (s ? T_7 : T_3) + 64 + 8 * lane, __byte_perm(v.x, em, 0x5432), __byte_perm(v.y, v.x, 0x7632));
    sts64(tb + (s ? T_9 : T_5) + 64 + 8 * lane, __byte_perm(v.y, e0, 0x5410), __byte_perm(e4, v.y, 0x5410));
  }
  __syncwarp();
}

__device__ __forceinline__ uint32_t box2w(int lo, int n, int o) {
  return ((unsigned)(o - lo) < (unsigned)n ? 0x3F80u : 0u) | ((unsigned)(o + 1 - lo) < (unsigned)n ? 0x3F800000u : 0u);
}

__device__ __forceinline__ void conv_channel(uint32_t ub, uint32_t tb, int lane, uint4* ydst) {
  const int g = lane >> 2, c = lane & 3, x = g - 2 * c;
  const int mi = lane >> 3;
  const uint32_t qa = ub + U_PAD + 16 * (lane & 7) + ((mi == 0 || mi == 3) ? U_ODD : 0) - (mi == 0 ? 16 : 0);
  const uint32_t hb = ub + U_PAD + (mi & 1) * U_ODD + 16 * ((lane >> 4) + (lane & 7)) - 16;
  const uint32_t kv = lds16(tb + T_KC + 16 + 2 * 512);
  const int oh = c < 2 ? 8 + 2 * c : 2 * c - 8, og = c < 3 ? 2 * c : -10;
  uint32_t bx[4] = {box2w(g - 4, 9, 2 * c), box2w(g - 3, 7, 2 * c), box2w(g - 4, 9, oh), box2w(g - 3, 7, oh)};
  uint32_t by[4] = {box2w(g - 10, 5, 2 * c - 8), box2w(g - 5, 3, 2 * c - 8), box2w(g - 10, 5, og), box2w(g - 5, 3, og)};
  uint32_t lb0 = ((unsigned)(x + 5) < 2u ? kv : 0u) | ((unsigned)(x + 4) < 2u ? kv << 16 : 0u);
  uint32_t lb1 = ((unsigned)(x - 3) < 2u ? kv : 0u) | ((unsigned)(x - 4) < 2u ? kv << 16 : 0u);
  const int q0 = g - 1, q1 = c < 3 ? g : g - 2;
  uint32_t y0a = ub + U_PAD + (q0 & 1) * U_ODD + 16 * (q0 >> 1) + 4 * c;
  uint32_t y1a = ub + U_PAD + (q1 & 1) * U_ODD + 16 * (q1 >> 1) + 4 * c;
#pragma unroll
  for (int i = 0; i < 4; i++) asm volatile("" : "+r"(bx[i]), "+r"(by[i]));
  asm volatile("" : "+r"(lb0), "+r"(lb1), "+r"(y0a), "+r"(y1a));
  mbar_wait(BAR(MB_UFULL));
  mbar_spin(BAR(MB_EMPTY + 15));
  TS(36);
  float acc[16][4];
  {
    uint32_t z09[8], z07[8], zm9[8], zm7[8];
#pragma unroll
    for (int i = 0; i < 8; i++) {
      uint32_t h[4];
      ldsm4(h, hb + 128 * i);
      float y0, y1, y2, y3, w0, w1, w2, w3;
      mma0(y0, y1, y2, y3, bx[0], bx[1], bx[2], bx[3], h[2], c < 2 ? h[3] : h[1]);
      mma0(w0, w1, w2, w3, bx[0], bx[1], bx[2], bx[3], h[1], c < 2 ? h[2] : h[0]);
      z09[i] = pack_bf(y0, y1); z07[i] = pack_bf(y2, y3);
      zm9[i] = pack_bf(w0, w1); zm7[i] = pack_bf(w2, w3);
    }
  uint32_t f3[3][4][4];
  {
    const uint32_t fa = tb + T_7 + 4 * (16 + x);
#pragma unroll
    for (int tt = 0; tt < 3; tt++)
#pragma unroll
      for (int D = 0; D < 4; D++) {
        const uint32_t a = fa + (tt == 0 ? 316 : (tt == 1 ? 320 : 0)) + 64 * D;
        f3[tt][D][0] = lds32(a); f3[tt][D][1] = lds32(a + 32); f3[tt][D][2] = lds32(a - 32); f3[tt][D][3] = lds32(a);
      }
  }
    SPLIT();
    nb_sync(NB_GATE, 256);
    SPLIT();
    float a[4][2][4];
#pragma unroll
    for (int kap = 0; kap < 4; kap++)
#pragma unroll
      for (int sg = 0; sg < 2; sg++)
#pragma unroll
        for (int bk = 3; bk >= kap; bk--) {
          const uint32_t(&q0_)[4] = f3[sg ? 2 : 0][bk - kap];
          const uint32_t(&q1_)[4] = f3[sg ? 2 : 1][bk - kap];
          float(&a0)[4] = a[bk][0];
          float(&a1)[4] = a[bk][1];
          if (sg == 0 && kap == 0) {
            mma0(a0[0], a0[1], a0[2], a0[3], q0_[0], q0_[1], q0_[2], q0_[3], z09[0], z09[1]);
            mma0(a1[0], a1[1], a1[2], a1[3], q1_[0], q1_[1], q1_[2], q1_[3], zm9[0], zm9[1]);
          } else {
            mma(a0[0], a0[1], a0[2], a0[3], q0_[0], q0_[1], q0_[2], q0_[3], sg ? zm7[2 * kap] : z09[2 * kap], sg ? zm7[2 * kap + 1] : z09[2 * kap + 1]);
            mma(a1[0], a1[1], a1[2], a1[3], q1_[0], q1_[1], q1_[2], q1_[3], sg ? z07[2 * kap] : zm9[2 * kap], sg ? z07[2 * kap + 1] : zm9[2 * kap + 1]);
          }
        }
    SPLIT();
#pragma unroll
    for (int i = 0; i < 8; i++) {
      uint32_t h[4];
      ldsm4(h, qa + 128 * i);
      const float ci[4] = {a[i >> 1][0][2 * (i & 1)], a[i >> 1][0][2 * (i & 1) + 1], a[i >> 1][1][2 * (i & 1)], a[i >> 1][1][2 * (i & 1) + 1]};
      mmac(acc[8 + i], h[0], h[1], h[2], h[3], lb0, lb1, ci);
    }
  }
  TS(44);
  {
    uint2 a5[10], a3[10];
    const uint32_t aa = tb + T_5 + 4 * (8 + 2 * g - 2 * c);
#pragma unroll
    for (int m = 0; m < 10; m++) { a5[m] = lds64(aa + 32 * m); a3[m] = lds64(aa + 384 + 32 * m); }
    uint32_t x5[12][2], x3[12][2];
    auto ygen = [&](int kap) {
#pragma unroll
      for (int hh = 0; hh < 2; hh++) {
        float y0, y1, y2, y3;
        mma0(y0, y1, y2, y3, by[0], by[1], by[2], by[3], lds32(y0a + 128 * kap + 64 * hh), lds32(y1a + 128 * kap + 64 * hh));
        x5[kap][hh] = pack_bf(y0, y1);
        x3[kap][hh] = pack_bf(y2, y3);
      }
    };
    ygen(11); ygen(10); ygen(9); ygen(8);
#pragma unroll
    for (int kap = 11; kap >= 0; kap--) {
      if (kap >= 4) ygen(kap - 4);
#pragma unroll
      for (int sg = 0; sg < 2; sg++)
#pragma unroll
        for (int i = 4; i >= 0; i--) {
          const int be = kap + 4 + i;
          if (be <= 15) {
            const uint2 &hi = sg ? a3[2 * i + 1] : a5[2 * i + 1], &lo = sg ? a3[2 * i] : a5[2 * i];
            const uint32_t b0 = sg ? x3[kap][0] : x5[kap][0], b1 = sg ? x3[kap][1] : x5[kap][1];
            if (be < 8 && i == 0 && sg == 0) mma0(acc[be][0], acc[be][1], acc[be][2], acc[be][3], hi.x, hi.y, lo.x, lo.y, b0, b1);
            else mma(acc[be][0], acc[be][1], acc[be][2], acc[be][3], hi.x, hi.y, lo.x, lo.y, b0, b1);
          }
        }
    }
  }
  TS(45);
  {
    const uint32_t st = tb + T_ST + lane * 8;
#pragma unroll
    for (int be = 4; be < 12; be++) sts64(st + 256 * be, pack_bf(acc[be][0], acc[be][1]), pack_bf(acc[be][2], acc[be][3]));
    SPLIT();
    uint32_t F[66], qd[8][4];
    const uint32_t fa = tb + T_D + 32 + 4 * x;
#pragma unroll
    for (int i = 0; i < 32; i++) {
      const int s = 120 - (i >> 2) - 8 * (i & 3);
      uint32_t(&q)[4] = qd[i & 7];
      ldsm4(q, qa + 16 * s);
      const int m = 16 * (i & 3) + 2 * (i >> 2);
      F[m] = lds32(fa + 32 * m); F[m + 1] = lds32(fa + 32 * m + 32);
#pragma unroll
      for (int be = 15; be >= 12; be--) {
        const int de = 8 * be - s;
        float(&a)[4] = (be >= 14 && !(i & 1)) ? acc[be - 4] : acc[be];
        if (de >= 0 && be >= 14 && i == 2 * (15 - be)) mma0(a[0], a[1], a[2], a[3], q[0], q[1], q[2], q[3], F[2 * de + 1], F[2 * de]);
        else if (de >= 0) mma(a[0], a[1], a[2], a[3], q[0], q[1], q[2], q[3], F[2 * de + 1], F[2 * de]);
      }
    }
#pragma unroll
    for (int i = 0; i < 8; i++) acc[14 + (i >> 2)][i & 3] += acc[10 + (i >> 2)][i & 3];
    F[64] = lds32(fa + 32 * 64); F[65] = lds32(fa + 32 * 65);
#pragma unroll
    for (int i = 0; i < 6; i++) ldsm4(qd[i], qa + 128 * 11 - 16 * i);
    uint2 sv = lds64(st + 256 * 11);
    float ci[4] = {bf_lo(sv.x), bf_hi(sv.x), bf_lo(sv.y), bf_hi(sv.y)};
    float T[5][4];
#pragma unroll
    for (int i = 0; i < 16; i++) T[i >> 2][i & 3] = acc[12 + (i >> 2)][i & 3];
    nb_sync(NB_YZ, 160);
    TS(46);
    uint32_t held[2];
#pragma unroll
    for (int be = 11; be >= 0; be--) {
      if (be & 1) SPLITN(be);
      const uint32_t qp = qa + 128 * be;
#pragma unroll
      for (int k = 4; k >= 1; k--) mmac(T[k], qd[0][0], qd[0][1], qd[0][2], qd[0][3], F[16 * k + 1], F[16 * k], T[k - 1]);
      if (be >= 4) mmac(T[0], qd[0][0], qd[0][1], qd[0][2], qd[0][3], F[1], F[0], ci);
      else mma0(T[0][0], T[0][1], T[0][2], T[0][3], qd[0][0], qd[0][1], qd[0][2], qd[0][3], F[1], F[0]);
      ldsm4(qd[6], qp - 16 * 6);
      ldsm4(qd[7], qp - 16 * 7);
      if (be > 4) sv = lds64(st + 256 * (be - 1));
#pragma unroll
      for (int i = 1; i < 8; i++) {
#pragma unroll
        for (int k = 3; k >= 0; k--)
          mma(T[k][0], T[k][1], T[k][2], T[k][3], qd[i][0], qd[i][1], qd[i][2], qd[i][3], F[16 * k + 2 * i + 1], F[16 * k + 2 * i]);
        if (i < 7 && be > 0) ldsm4(qd[i - 1], qp - 128 - 16 * (i - 1));
        if (i == 2) {
          const uint32_t w0 = pack_bf(T[4][0], T[4][1]), w1 = pack_bf(T[4][2], T[4][3]);
          if (be & 1) { held[0] = w0; held[1] = w1; }
          else st_x(ydst + (be + 4) * 16, nz(w0), w1, held[0], held[1]);
          if ((be & 3) == 3 && be < 11) nb_arrive(NB_Y + 2 + (be >> 2), 160);
        }
        if (i == 4 && be > 4) { ci[0] = bf_lo(sv.x); ci[1] = bf_hi(sv.x); ci[2] = bf_lo(sv.y); ci[3] = bf_hi(sv.y); }
      }
    }
    if ((fu(T[0][0]) & fu(T[1][0]) & fu(T[2][0]) & fu(T[3][0])) == 0xffffffffu) sts32(st, 0);
    nb_arrive(NB_BDONE, 288);
    nb_arrive(NB_Y + 1, 160);
#pragma unroll
    for (int B = 1; B >= 0; B--)
      st_x(ydst + B * 32, nz(pack_bf(T[2 * B][0], T[2 * B][1])), pack_bf(T[2 * B][2], T[2 * B][3]),
           pack_bf(T[2 * B + 1][0], T[2 * B + 1][1]), pack_bf(T[2 * B + 1][2], T[2 * B + 1][3]));
  }
}

__device__ __forceinline__ void dual_exp(const uint32_t* w, uint32_t* e) {
  const float L = 1.44268798828125f;
  uint32_t mx = bmax2(bmax2(w[0], w[1]), bmax2(w[2], w[3]));
  uint32_t mn = bmin2(bmin2(w[0], w[1]), bmin2(w[2], w[3]));
  mx = bmax2(mx, __shfl_xor_sync(0xffffffffu, mx, 1));
  mn = bmin2(mn, __shfl_xor_sync(0xffffffffu, mn, 1));
  mx = bmax2(mx, __shfl_xor_sync(0xffffffffu, mx, 2));
  mn = bmin2(mn, __shfl_xor_sync(0xffffffffu, mn, 2));
  const float mx0 = bf_lo(mx) * -L, mx1 = bf_hi(mx) * -L, mn0 = bf_lo(mn) * L, mn1 = bf_hi(mn) * L;
#pragma unroll
  for (int i = 0; i < 2; i++) {
    const float a0 = bf_lo(w[2 * i]), a1 = bf_hi(w[2 * i]), b0 = bf_lo(w[2 * i + 1]), b1 = bf_hi(w[2 * i + 1]);
    e[2 * i] = pack_bf(ex2(fmaf(a0, L, mx0)), ex2(fmaf(b0, L, mx0)));
    e[2 * i + 1] = pack_bf(ex2(fmaf(a1, L, mx1)), ex2(fmaf(b1, L, mx1)));
    e[4 + 2 * i] = pack_bf(ex2(fmaf(a0, -L, mn0)), ex2(fmaf(b0, -L, mn0)));
    e[5 + 2 * i] = pack_bf(ex2(fmaf(a1, -L, mn1)), ex2(fmaf(b1, -L, mn1)));
  }
}
__device__ __forceinline__ void normalise(uint32_t* e, const float (&s)[4]) {
  const uint32_t r = pack_bf(rcp(s[0]), rcp(s[2]));
  const __nv_bfloat162 rr = *(const __nv_bfloat162*)&r;
#pragma unroll
  for (int i = 0; i < 4; i++) {
    const __nv_bfloat162 v = __hmul2(*(const __nv_bfloat162*)&e[i], (i & 1) ? __high2bfloat162(rr) : __low2bfloat162(rr));
    e[i] = *(const uint32_t*)&v;
  }
}
__host__ __device__ constexpr uint64_t qdesc(uint32_t addr) { return mkdesc(addr, 128, 256, 0); }

__global__ void __launch_bounds__(NTHREADS, 1)
fused_kernel(const Params P, const __grid_constant__ CUtensorMap mx, const __grid_constant__ CUtensorMap mw,
             const __grid_constant__ CUtensorMap mo, const __grid_constant__ CUtensorMap mu,
             const __grid_constant__ CUtensorMap mout, const __grid_constant__ CUtensorMap mut) {
  constexpr uint32_t sb = SB;
  const int tid = threadIdx.x, lane = tid & 31;
  const int warp = __shfl_sync(0xffffffffu, tid >> 5, 0);
  const int b = blockIdx.x, oct = b >> 3, i8 = b & 7;
  const int rt = (((oct & 4) ? ~oct : oct) & 3) * 2 + (i8 >> 2);
  const int hp = (oct >> 2) * 4 + (i8 & 3);

  const int wg = warp >> 2, w = warp & 3;
  const int d = b * 4 + ((tid >> 5) & 3);
  const KgenRaw raw = kgen_load(P, d, (tid >> 7) & 1, lane, (tid + 128) & 256);
  const uint32_t tb = sb + OFF_T + w * T_CH;
  if (warp >= 12) {
    asm volatile("setmaxnreg.dec.sync.aligned.u32 32;");
    if (warp == 12) {
      if (lane == 0) {
#pragma unroll
        for (int i = 0; i < 9; i++) mbar_init(BAR(i), 1);
        asm volatile("fence.mbarrier_init.release.cluster;" ::: "memory");
      }
      __syncwarp();
      if (lane < 9) mbar_expect(BAR(0) + 8 * lane, lane == 0 ? 16384 : 28672);
      __syncwarp();
      nb_arrive(NB_PROD, 512);
#pragma unroll 1
      for (int kb = 0; kb < 8; kb++) {
        if (kb == U_AT) e_tma4d(sb + OFF_STG0, &mu, BAR(MB_URAW), i8 * 64, oct * 2);
        e_tma3d(sb + OFF_W + kb * 12288, &mw, BAR(MB_FULL) + 8 * kb, hp * 32, kb * 64, 0);
        if (kb < 5) e_tma2d(sb + OFF_X + (kb < 2 ? kb + 3 : kb - 2) * 16384, &mx, BAR(MB_FULL) + 8 * kb, kb * 64, rt * 256);
      }
      if (U_AT == 8) e_tma4d(sb + OFF_STG0, &mu, BAR(MB_URAW), i8 * 64, oct * 2);
      if (smem_u32(smem_raw) != SB) __trap();
      if (lane == 0) TS1(54);
      nb_sync(NB_GATE + 1, 64);
      e_prefetch(P.x + (size_t)(rt * 256 + 128 + hp * 8) * 512, 8192);
      uint32_t slot = sb + OFF_X + 3 * 16384;
#pragma unroll 1
      for (int n = 0; n < 11; n++) {
        mbar_spin(BAR(MB_EMPTY) + 8 * n);
        const int m = n + 5;
        e_tma2d(slot, &mx, BAR(MB_FULL) + 8 * m, (m & 7) * 64, rt * 256 + (m >> 3) * 128);
        slot = slot == sb + OFF_X + 4 * 16384 ? sb + OFF_X : slot + 16384;
        if (n == 7) {
          e_prefetch(P.wo + (size_t)b * 2048, 4096);
          asm volatile("prefetch.tensormap [%0];" ::"l"(&mo) : "memory");
          asm volatile("prefetch.tensormap [%0];" ::"l"(&mout) : "memory");
        }
      }
      mbar_wait(BAR(MB_UFULL));
#pragma unroll 1
      for (int i = 0; i < 8; i++) {
        mbar_wait(BAR(MB_EMPTY + 10) + 8 * ((0x54332222u >> (4 * i)) & 7));
        const int w0 = (0x54736210u >> (4 * i)) & 7;
        e_tma3d(sb + OFF_W + w0 * 16384, &mo, BAR(MB_WO), 0, w0 * 64, (hp & 3) * 2);
      }
    } else {
      if (warp == 13) {
        if (lane == 0) {
#pragma unroll
          for (int i = 9; i < 40; i++) mbar_init(BAR(i), (i < MB_EMPTY || i == MB_AUX) ? 1 : 4);
          asm volatile("fence.mbarrier_init.release.cluster;" ::: "memory");
        }
        __syncwarp();
        if (lane < 14 && lane != 9) mbar_expect(BAR(MB_FULL + 8) + 8 * lane, lane == 8 ? 131072 : (lane == 10 ? 8192 : (lane == 13 ? 24576 : 16384)));
        nb_arrive(NB_GATE + 1, 64);
      } else if (warp == 14) {
        asm volatile("prefetch.tensormap [%0];" ::"l"(&mw) : "memory");
        asm volatile("prefetch.tensormap [%0];" ::"l"(&mx) : "memory");
        asm volatile("prefetch.tensormap [%0];" ::"l"(&mu) : "memory");
        asm volatile("prefetch.tensormap [%0];" ::"l"(&mut) : "memory");
        e_prefetch(P.x + (size_t)(rt * 256 + hp * 8) * 512, 8192);
      }
      nb_sync(NB_PROD, 512);
      if (warp == 15) {
        const uint4 v0 = __ldg((const uint4*)P.wphi + hp * 64 + lane), v1 = __ldg((const uint4*)P.wphi + hp * 64 + 32 + lane);
        sts128(sb + OFF_PHI + (lane & 1) * 256 + (lane >> 1) * 16, v0.x, v0.y, v0.z, v0.w);
        sts128(sb + OFF_PHI + 512 + (lane & 1) * 256 + (lane >> 1) * 16, v1.x, v1.y, v1.z, v1.w);
        const uint32_t one = (((lane >> 3) ^ (lane >> 4)) & 1) ? 0u : ((lane & 1) ? 0x3F800000u : 0x3F80u);
        const int q = (lane >> 1) & 3;
        sts128(sb + OFF_EYE + lane * 16, q == 0 ? one : 0u, q == 1 ? one : 0u, q == 2 ? one : 0u, q == 3 ? one : 0u);
        sts64(sb + OFF_ONE + lane * 8, 0x3F803F80u, 0x3F803F80u);
        asm volatile("fence.proxy.async.shared::cta;" ::: "memory");
        nb_arrive(NB_KREAD, 160);
      }
      uint32_t* cnt = (uint32_t*)(P.xs + X_CNT) + (warp == 13 ? i8 : (warp == 14 ? 8 + rt : 16 + oct)) * 32;
      const unsigned target = (ld_x32(cnt) & ~15u) + 16;
      if (warp != 14) {
        if (warp == 15) mbar_wait(BAR(MB_EMPTY + ZERO_STEP));
        uint4* pz = P.xs + (warp == 13 ? X_PART + (hp * 8 + rt) * 144 : X_Y + b * 1024) + lane;
#pragma unroll 1
        for (int i = (warp == 13 ? 144 : 1024) - lane; i > 0; i -= 32, pz += 32) st_x(pz, 0, 0, 0, 0);
      }
      if (warp == 15) __syncwarp();
      else nb_sync(warp == 13 ? NB_INIT : NB_ODONE, warp == 13 ? 160 : 288);
      if (warp == 13) {
        if (lane == 0) TS1(49);
        if (STORE_AT >= 0) mbar_wait(BAR(MB_EMPTY + (STORE_AT >= 0 ? STORE_AT : 0)));
        if (lane == 0) {
          asm volatile("cp.async.bulk.tensor.3d.global.shared::cta.bulk_group [%0, {%2,%4,%3}], [%1];\n"
                       "cp.async.bulk.commit_group;\ncp.async.bulk.wait_group 0;\nfence.proxy.async.global;\n"
                       ::"l"(&mut), "r"(sb + OFF_STG0), "r"(oct * 64), "r"(i8 * 64), "r"(0) : "memory");
          mbar_arrive(BAR(MB_AUX));
        }
      }
      if (lane == 0) asm volatile("red.release.gpu.global.add.u32 [%0], %1;" ::"l"(cnt), "r"(warp == 15 ? 2 : 1) : "memory");
      if (lane == 0) TS1(warp == 13 ? 50 : (warp == 14 ? 57 : 53));
      __syncwarp();
      if (warp == 14) nb_arrive(NB_GATE + 1, 160);
      asm volatile("fence.proxy.async.shared::cta;" ::: "memory");
      if (warp == 13) cnt += ((lane & 1 ? b >> 4 : i8 ^ (lane & 4)) - i8) * 32;
#pragma unroll 1
      for (int i = 0; i < SPIN_MAX; i++) {
        unsigned v;
        asm volatile("ld.acquire.gpu.global.u32 %0, [%1];" : "=r"(v) : "l"(cnt) : "memory");
        if (__all_sync(0xffffffffu, (int)(v - target) >= 0)) break;
      }
      if (lane == 0) TS1(warp == 13 ? 51 : (warp == 14 ? 58 : 55));
      if (warp == 15) { nb_arrive(NB_YZ, 160); return; }
      asm volatile("fence.proxy.async.global;" ::: "memory");
      if (warp == 13) {
        mbar_wait(BAR(MB_EMPTY + 11));
        e_expect(BAR(MB_UFULL), 4 * U_CH);
        e_bulk(sb + OFF_U, P.xs + X_UT + b * (U_CH / 4), 4 * U_CH, BAR(MB_UFULL));
      } else {
        const uint4* src = P.xs + X_O + (rt * 4 + (hp >> 2)) * 4096;
        e_bulk(sb + OFF_X + 32768 + 57344, src + 3584, 8192, BAR(MB_O));
        e_bulk(sb + OFF_X + 32768, src, 16384, BAR(MB_O + 1));
        e_bulk(sb + OFF_X + 49152, src + 1024, 16384, BAR(MB_O + 2));
        e_bulk(sb + OFF_STG0, src + 3200, 6144, BAR(MB_O + 3));
        nb_sync(NB_BDONE, 288);
        asm volatile("fence.proxy.async.shared::cta;" ::: "memory");
        e_bulk(sb + OFF_U, src + 2048, 18432, BAR(MB_O + 3));
      }
    }
    return;
  }

  asm volatile("setmaxnreg.inc.sync.aligned.u32 160;");
  const int t = tid & 127;
  const int g = lane >> 2, c = lane & 3;
  const uint32_t kp = ((tb + 127) & ~127u) + (wg & 1) * 2048;
  const KgenAddr kad = kgen_addr(lane, kp);
  nb_sync(NB_PROD, 512);
  SPLIT();
  float k[5][4], k2048, ksc;
  if (wg) {
    kgen_unit(raw, kad, blockIdx.y, k, k2048, ksc);
    TS(40 + wg);
    if ((fu(k[0][0]) & fu(k[1][0]) & fu(k[2][0]) & fu(k[3][0]) & fu(k[4][0])) == 0xffffffffu) sts32(kp, 0);
  }
  if (wg) nb_arrive(0, 384);
  if (wg) {
    if (wg == 1) {
      uint32_t h[10];
#pragma unroll
      for (int j = 0; j < 10; j++) h[j] = hu(__floats2half2_rn(k[j >> 1][2 * (j & 1)], k[j >> 1][2 * (j & 1) + 1]));
      sts128(kp + lane * 16, h[0], h[1], h[2], h[3]);
      sts128(kp + 512 + lane * 16, h[4], h[5], h[6], h[7]);
      sts128(kp + 1024 + lane * 16, h[8], h[9], fu(k2048), fu(ksc));
      nb_arrive(NB_PREP, 256);
    }
  } else {
    mbar_wait(BAR(MB_URAW));
    TS(48);
    const int ln = ((lane >> 1) & 3) + 4 * (lane & 1);
    uint32_t r[8][4];
#pragma unroll
    for (int i = 0; i < 8; i++) ldsm4t(r[i], sb + OFF_STG0 + w * 4096 + ((lane >> 3) * 8 + ln) * 128 + ((i ^ ln) << 4));
    nb_sync(NB_HAND, 128);
    const uint32_t dst = sb + OFF_STG0 + (2 * g + (w & 1)) * 128 + ((((w >> 1) * 4 + c) ^ ((2 * g + (w & 1)) & 7)) << 4);
#pragma unroll
    for (int i = 0; i < 8; i++) sts128(dst + i * 2048, r[i][0], r[i][1], r[i][2], r[i][3]);
    asm volatile("fence.proxy.async.shared::cta;" ::: "memory");
    nb_arrive(NB_INIT, 160);
  }
  {
    if (wg == 2) {
#pragma unroll
      for (int j = 0; j < 5; j++) { k[j][0] *= ksc; k[j][1] *= ksc; k[j][2] *= ksc; k[j][3] *= ksc; }
      const unsigned short dsk = __ldg((const unsigned short*)P.Dskip + d);
      nb_sync(NB_PREP, 256);
      {
        const uint32_t src = kp + 2048 + lane * 16;
        const uint4 v0 = lds128(src), v1 = lds128(src + 512), v2 = lds128(src + 1024);
        const uint32_t h[10] = {v0.x, v0.y, v0.z, v0.w, v1.x, v1.y, v1.z, v1.w, v2.x, v2.y};
#pragma unroll
        for (int j = 0; j < 10; j++) {
          const float2 f = __half22float2(*(const __half2*)&h[j]);
          k[j >> 1][2 * (j & 1)] = fmaf(f.x, uf(v2.w), k[j >> 1][2 * (j & 1)]);
          k[j >> 1][2 * (j & 1) + 1] = fmaf(f.y, uf(v2.w), k[j >> 1][2 * (j & 1) + 1]);
        }
        k2048 += uf(v2.z);
      }
#pragma unroll
      for (int o2 = 16; o2; o2 >>= 1) k2048 += __shfl_xor_sync(0xffffffffu, k2048, o2);
      if (lane == 0) k[0][0] += bf_lo(dsk);
      __syncwarp();
      TS(34);
      build_tables(tb, lane, k, k2048);
      TS(35);
      uint4* const g_y = P.xs + X_Y;
      conv_channel(sb + OFF_U + w * U_CH, tb, lane, g_y + (size_t)d * 256 + lane);
      nb_arrive(NB_Y, 160);
      TS(37);
      if (w == 0) TSDUMP(32);
      return;
    }
    if (wg == 1) {
      mbar_wait(BAR(MB_EMPTY + 4));
      mbar_spin(BAR(MB_EMPTY + 6));
    }
    TS(wg * 16 + 1);
  }

  float acc[2][48];
  {
    uint32_t fb = BAR(MB_FULL) + 64 * wg;
    uint32_t da = (uint32_t)mkdesc(sb + OFF_X, 16, 0, 0) + (wg ? 1024 : 3072), db = (uint32_t)mkdesc(sb + OFF_W, 4096, 0, 0);
    constexpr uint64_t ha = mkdesc(0, 0, 1024, 1), hb = mkdesc(0, 0, 512, 2);
    mbar_spin(fb);
    if (wg == 0) nb_sync(0, 384);
    TS(wg * 16 + 2);
#pragma unroll 1
    for (int kb = 0; kb < 8; kb++) {
      WG_FENCE();
#pragma unroll
      for (int k = 0; k < 4; k++) {
        wgmma_ss_n96(acc[0], ha | (da + 2 * k), hb | (db + 64 * k), k ? 1 : kb);
        wgmma_ss_n96(acc[1], ha | (da + 2 * k + 512), hb | (db + 64 * k), k ? 1 : kb);
      }
      WG_COMMIT();
      if (kb < 7) mbar_spin(fb + 8);
      WG_WAIT(1);
      if (kb > 0) e_arrive(fb + 8 * (MB_EMPTY - MB_FULL - 1));
      fb += 8; db += 768;
      da = da == (uint32_t)mkdesc(sb + OFF_X + 65536, 16, 0, 0) ? da - 4096 : da + 1024;
    }
    if (wg == 0) nb_sync(NB_KREAD, 160);
    WG_WAIT(0);
    e_arrive(fb + 8 * (MB_EMPTY - MB_FULL - 1));
    SPLIT();
  }
  TS(wg * 16 + 3);

  constexpr uint32_t stg0 = sb + OFF_STG0, stg1 = sb + OFF_X + 32768;
  uint4* const g_part = P.xs + X_PART;
  uint4* const g_o = P.xs + X_O;
  constexpr uint32_t kvs = stg0;
  auto pack8 = [](const float* a) { return make_uint4(pack_bf(a[0], a[1]), pack_bf(a[2], a[3]), pack_bf(a[4], a[5]), pack_bf(a[6], a[7])); };
  auto stage_k = [&](auto nt, const uint4* af, const uint4* vp, uint32_t sl, uint32_t free_bar) {
    constexpr int NU = 2 * decltype(nt)::value;
    float p[NU][8], rs[2 * NU][4];
    uint32_t ek[8 * NU];
    WG_FENCE();
#pragma unroll
    for (int u = 0; u < NU; u++) wgmma_rs_n16(p[u], af[u], qdesc(sb + OFF_PHI + (u & 1) * 512), 0);
    WG_COMMIT();
    WG_WAIT(0);
#pragma unroll
    for (int u = 0; u < NU; u++) {
      const uint32_t pw[4] = {pack_bf(p[u][0], p[u][2]), pack_bf(p[u][1], p[u][3]), pack_bf(p[u][4], p[u][6]), pack_bf(p[u][5], p[u][7])};
      dual_exp(pw, ek + 8 * u);
    }
    TS(wg * 16 + 12);
    mbar_spin(free_bar);
    WG_FENCE();
#pragma unroll
    for (int i = 0; i < 2 * NU; i++) wgmma_rs_n8(rs[i], make_uint4(ek[4 * i], ek[4 * i + 1], ek[4 * i + 2], ek[4 * i + 3]), qdesc(sb + OFF_ONE), 0);
    WG_COMMIT();
#pragma unroll
    for (int i = 0; i < NU; i++) stsm4(sl + (i >> 1) * 4 * SLAB + 2048 + (i & 1) * 512, vp[i].x, vp[i].y, vp[i].z, vp[i].w);
    if (NU == 4 || lane < 16) sts128(sl + (lane >> 4) * (4 * SLAB - 256) + 3072, 0x3F803F80u, 0x3F803F80u, 0x3F803F80u, 0x3F803F80u);
    WG_WAIT(0);
#pragma unroll
    for (int i = 0; i < 2 * NU; i++) {
      normalise(ek + 4 * i, rs[i]);
      stsm4(sl + (i >> 2) * 4 * SLAB + (i & 3) * 512, ek[4 * i], ek[4 * i + 1], ek[4 * i + 2], ek[4 * i + 3]);
    }
    asm volatile("fence.proxy.async.shared::cta;" ::: "memory");
  };
  auto contract = [&](float (&kc)[20], uint32_t stg, int acc_in) {
    WG_FENCE();
#pragma unroll
    for (int s = 0; s < 8; s++) wgmma_ss_n40(kc, qdesc(stg + s * SLAB), qdesc(stg + s * SLAB + 2048), s ? 1 : acc_in);
    WG_COMMIT();
    WG_WAIT(0);
  };
  uint32_t eq[32];
  {
    uint4 af[4], aq[4], vp[4];
    float kc[20];
#pragma unroll
    for (int u = 0; u < 4; u++) { af[u] = pack8(acc[u >> 1] + 16 + 8 * (u & 1)); vp[u] = pack8(acc[u >> 1] + 32 + 8 * (u & 1)); }
    const uint32_t hand = stg1 + 16384 + 8192 + w * 2048 + lane * 16;
    if (wg) {
      sts128(hand, af[2].x, af[2].y, af[2].z, af[2].w); sts128(hand + 512, af[3].x, af[3].y, af[3].z, af[3].w);
      sts128(hand + 1024, vp[2].x, vp[2].y, vp[2].z, vp[2].w); sts128(hand + 1536, vp[3].x, vp[3].y, vp[3].z, vp[3].w);
      nb_arrive(NB_HAND, 256);
    }
#pragma unroll
    for (int u = 0; u < 4; u++) aq[u] = pack8(acc[u >> 1] + 8 * (u & 1));
    if (wg == 0) {
      stage_k(std::integral_constant<int, 2>(), af, vp, stg0 + w * SLAB + lane * 16, BAR(MB_AUX));
      TS(13);
      nb_sync(NB_WG0, 128);
      contract(kc, stg0, 0);
      mbar_wait(BAR(MB_UFULL));
      TS(15);
      nb_sync(NB_HAND, 256);
      af[0] = lds128(hand); af[1] = lds128(hand + 512); vp[0] = lds128(hand + 1024); vp[1] = lds128(hand + 1536);
      nb_sync(NB_WG0, 128);
    }
    stage_k(std::integral_constant<int, 1>(), af, vp, stg1 + (wg ? w : 4 + w) * SLAB + lane * 16, BAR(MB_EMPTY + 15));
    TS(wg * 16 + 14);
    float p[4][8];
    if (wg) {
      nb_arrive(NB_ST0, 256);
      nb_arrive(NB_GATE, 256);
    } else {
      uint4* pp = g_part + (size_t)(hp * 8 + rt) * 144 + t;
      uint32_t* pz = (uint32_t*)(pp - t + 128) + w * 16 + c * 8 + g;
      asm volatile("" : "+l"(pp), "+l"(pz));
      nb_sync(NB_ST0, 256);
      contract(kc, stg1, 1);
      TS(6);
      float kv[8];
#pragma unroll
      for (int i = 0; i < 8; i++) kv[i] = w & 2 ? kc[8 + i] : kc[i];
      st_x(pp, nz(pack_bf(kv[0], kv[1])), pack_bf(kv[2], kv[3]), pack_bf(kv[4], kv[5]), pack_bf(kv[6], kv[7]));
      if (c < 2) st_x32(pz, nz(fu(c ? kc[18] : kc[16])));
      TS(5);
    }
    SPLIT();
    WG_FENCE();
#pragma unroll
    for (int u = 0; u < 4; u++) wgmma_rs_n16(p[u], aq[u], qdesc(sb + OFF_PHI + (u & 1) * 512), 0);
    WG_COMMIT();
    WG_WAIT(0);
#pragma unroll
    for (int u = 0; u < 4; u++) {
      const uint32_t pw[4] = {pack_bf(p[u][0], p[u][2]), pack_bf(p[u][1], p[u][3]), pack_bf(p[u][4], p[u][6]), pack_bf(p[u][5], p[u][7])};
      dual_exp(pw, eq + 8 * u);
    }
    SPLIT();
  }
  TS(wg * 16 + 4);
  if (wg == 1) {
    mbar_wait(BAR(MB_UFULL));
    const uint4* ps = g_part + (size_t)hp * 8 * 144 + t;
    const uint32_t* zs = (const uint32_t*)(g_part + (size_t)(hp * 8 + (lane >> 4) * 4) * 144 + 128) + w * 16 + (lane & 15);
    uint4 v[8];
    uint32_t zv[4];
#pragma unroll 1
    for (int it = 0; it < SPIN_MAX; it++) {
#pragma unroll
      for (int i = 0; i < 8; i++) v[i] = ld_x(ps + i * 144);
#pragma unroll
      for (int i = 0; i < 4; i++) zv[i] = ld_x32(zs + i * 576);
      uint32_t m = min(min(zv[0], zv[1]), min(zv[2], zv[3]));
#pragma unroll
      for (int i = 0; i < 8; i++) m = min(m, v[i].x);
      if (__all_sync(0xffffffffu, m != 0)) break;
    }
    float s[8];
    WG_FENCE();
#pragma unroll
    for (int r = 0; r < 8; r++) wgmma_rs_n16(s, v[r], qdesc(sb + OFF_EYE), r);
    WG_COMMIT();
    float zsum = (uf(zv[0]) + uf(zv[1])) + (uf(zv[2]) + uf(zv[3]));
    zsum += __shfl_xor_sync(0xffffffffu, zsum, 16);
    const uint32_t z1 = pack_bf(zsum, 1.f);
    if (lane < 16) sts128(kvs + w * 768 + 512 + lane * 16, z1, z1, z1, z1);
    WG_WAIT(0);
    stsm4(kvs + w * 768 + lane * 16, pack_bf(s[0], s[1]), pack_bf(s[2], s[3]), pack_bf(s[4], s[5]), pack_bf(s[6], s[7]));
    asm volatile("fence.proxy.async.shared::cta;" ::: "memory");
    TS(22);
  }
  nb_sync(NB_KV, 256);
  {
    float n[8][12];
    WG_FENCE();
#pragma unroll
    for (int i = 0; i < 8; i++) wgmma_rs_n24(n[i], make_uint4(eq[4 * i], eq[4 * i + 1], eq[4 * i + 2], eq[4 * i + 3]), qdesc(kvs + (i & 3) * 768), 0);
    WG_COMMIT();
    uint32_t* od = (uint32_t*)(g_o + (size_t)((rt * 4 + wg * 2) * 32 + hp * 2) * 128) + w * 64 + lane;
    WG_WAIT(0);
#pragma unroll
    for (int u = 0; u < 4; u++) {
      float(&np)[12] = n[2 * u];
      const float(&nm)[12] = n[2 * u + 1];
      const float q0 = np[9] * rcp(nm[9]), q1 = np[11] * rcp(nm[11]);
      const float r0 = rcp(fmaf(nm[8], q0, fmaf(np[9], 1e-6f, np[8]))), r1 = rcp(fmaf(nm[10], q1, fmaf(np[11], 1e-6f, np[10])));
#pragma unroll
      for (int i = 0; i < 8; i++) np[i] = fmaf(nm[i], (i & 2) ? q1 : q0, np[i]);
      uint32_t* o = od + (u >> 1) * 16384 + (u & 1) * 512;
      o[0] = pack_bf(np[0] * r0, np[1] * r0);
      o[32] = pack_bf(np[2] * r1, np[3] * r1);
      o[256] = pack_bf(np[4] * r0, np[5] * r0);
      o[288] = pack_bf(np[6] * r1, np[7] * r1);
      if (u == 1) SPLIT();
    }
  }
  TS(wg * 16 + 7);
  nb_arrive(NB_ODONE, 288);
  if (wg) {
    const uint4* src = P.xs + X_Y + (oct * 32 + c * 8) * 256 + (2 * w + (g >> 2)) * 32 + i8 * 4 + (g & 3);
    __nv_bfloat16* dst = P.out + (size_t)((2 * w + (g >> 2)) * 256 + i8 * 16 + (g & 3) * 2) * 1024 + 512 + oct * 32 + c * 8;
    nb_sync(NB_GATE + 1, 160);
    nb_sync(NB_Y + w, 160);
    uint4 v[8];
#pragma unroll 1
    for (int it = 0; it < SPIN_MAX; it++) {
      uint32_t m = 0xffffffffu;
#pragma unroll
      for (int i = 0; i < 8; i++) v[i] = ld_x(src + i * 256);
#pragma unroll
      for (int i = 0; i < 8; i++) m = min(m, v[i].x);
      if (__all_sync(0xffffffffu, m != 0)) break;
    }
#pragma unroll
    for (int i = 0; i < 8; i++) *(uint4*)(dst + (size_t)((i >> 2) * 128 + ((i >> 1) & 1) * 8 + (i & 1)) * 1024) = tr_row(v, i);
    TS(31);
    GT(63);
    if (w == 0) TSDUMP(16);
    return;
  }
  mbar_wait(BAR(MB_WO));
  nb_sync(NB_BDONE, 288);
  TS(8);
  mbar_spin(BAR(MB_O));
  TS(9);
  constexpr uint64_t ha = mkdesc(0, 0, 128, 0), hb = mkdesc(0, 0, 1024, 1);
  constexpr uint32_t da0 = (uint32_t)mkdesc(stg1, 1024, 0, 0), db0 = (uint32_t)mkdesc(sb + OFF_W, 8192, 0, 0);
  const uint32_t ot = ((sb + OFF_T + 1023) & ~1023u) + w * 4096;
  auto store_half = [&](const float* oc, int hf) {
#pragma unroll
    for (int i = 0; i < 8; i += 2)
      stsm4(ot + hf * 2048 + (lane & 15) * 128 + (((i + (lane >> 4)) ^ lane) & 7) * 16, pack_bf(oc[4 * i], oc[4 * i + 1]),
            pack_bf(oc[4 * i + 2], oc[4 * i + 3]), pack_bf(oc[4 * i + 4], oc[4 * i + 5]), pack_bf(oc[4 * i + 6], oc[4 * i + 7]));
    asm volatile("fence.proxy.async.shared::cta;" ::: "memory");
    __syncwarp();
    e_store2d(&mout, ot + hf * 2048, (hp & 3) * 128 + hf * 64, (rt * 4 + (hp >> 2)) * 64 + w * 16);
  };
  float oc[64];
#pragma unroll 1
  for (int j = 0; j < 8; j++) {
    const int kb = (j + 7) & 7;
    if ((j & 1) && j < 6) mbar_spin(BAR(MB_O + 1) + 4 * (j - 1));
    WG_FENCE();
#pragma unroll
    for (int k = 0; k < 4; k++) wgmma_ss_n128(oc, ha | (da0 + 512 * kb + 128 * k), hb | (db0 + 1024 * kb + 128 * k), k ? 1 : j);
    WG_COMMIT();
  }
  WG_WAIT(0);
  TS(10);
  store_half(oc, 0);
  store_half(oc + 32, 1);
  asm volatile(ELECT "cp.async.bulk.commit_group;\n@p cp.async.bulk.wait_group.read 0;\n}\n" ::: "memory");
  TS(wg * 16 + 11);
  GT(61 + wg);
  if (w == 0) TSDUMP(0);
  if (w == 1) TSDUMP(48);
}

typedef CUresult (*EncodeFn)(CUtensorMap*, CUtensorMapDataType, cuuint32_t, void*, const cuuint64_t*, const cuuint64_t*,
                             const cuuint32_t*, const cuuint32_t*, CUtensorMapInterleave, CUtensorMapSwizzle,
                             CUtensorMapL2promotion, CUtensorMapFloatOOBfill);

}

extern "C" void kernel_launch(void* const* d_in, const int* in_sizes, int n_in, void* d_out, int out_size) {
  (void)in_sizes; (void)n_in; (void)out_size;
  void* fn = nullptr;
  cudaDriverEntryPointQueryResult qr;
  cudaGetDriverEntryPoint("cuTensorMapEncodeTiled", &fn, cudaEnableDefault, &qr);
  EncodeFn enc = (EncodeFn)fn;
  CUtensorMap mx, mw, mo, mu, mout, mut;
  const cuuint32_t es[5] = {1, 1, 1, 1, 1};
  {
    cuuint64_t dims[2] = {512, 2048}, st[1] = {1024};
    cuuint32_t box[2] = {64, 128};
    enc(&mx, CU_TENSOR_MAP_DATA_TYPE_BFLOAT16, 2, d_in[0], dims, st, box, es, CU_TENSOR_MAP_INTERLEAVE_NONE,
        CU_TENSOR_MAP_SWIZZLE_128B, CU_TENSOR_MAP_L2_PROMOTION_L2_128B, CU_TENSOR_MAP_FLOAT_OOB_FILL_NONE);
  }
  {
    cuuint64_t dims[3] = {512, 512, 3}, st[2] = {3072, 1024};
    cuuint32_t box[3] = {32, 64, 3};
    enc(&mw, CU_TENSOR_MAP_DATA_TYPE_BFLOAT16, 3, d_in[1], dims, st, box, es, CU_TENSOR_MAP_INTERLEAVE_NONE,
        CU_TENSOR_MAP_SWIZZLE_64B, CU_TENSOR_MAP_L2_PROMOTION_L2_128B, CU_TENSOR_MAP_FLOAT_OOB_FILL_NONE);
  }
  {
    cuuint64_t dims[3] = {64, 512, 8}, st[2] = {1024, 128};
    cuuint32_t box[3] = {64, 64, 2};
    enc(&mo, CU_TENSOR_MAP_DATA_TYPE_BFLOAT16, 3, d_in[3], dims, st, box, es, CU_TENSOR_MAP_INTERLEAVE_NONE,
        CU_TENSOR_MAP_SWIZZLE_128B, CU_TENSOR_MAP_L2_PROMOTION_L2_128B, CU_TENSOR_MAP_FLOAT_OOB_FILL_NONE);
  }
  {
    cuuint64_t dims[4] = {512, 4, 16, 32}, st[3] = {16384, 1024, 65536};
    cuuint32_t box[4] = {64, 4, 16, 2};
    enc(&mu, CU_TENSOR_MAP_DATA_TYPE_BFLOAT16, 4, d_in[4], dims, st, box, es, CU_TENSOR_MAP_INTERLEAVE_NONE,
        CU_TENSOR_MAP_SWIZZLE_128B, CU_TENSOR_MAP_L2_PROMOTION_L2_128B, CU_TENSOR_MAP_FLOAT_OOB_FILL_NONE);
  }
  {
    cuuint64_t dims[2] = {1024, 2048}, st[1] = {2048};
    cuuint32_t box[2] = {64, 16};
    enc(&mout, CU_TENSOR_MAP_DATA_TYPE_BFLOAT16, 2, d_out, dims, st, box, es, CU_TENSOR_MAP_INTERLEAVE_NONE,
        CU_TENSOR_MAP_SWIZZLE_128B, CU_TENSOR_MAP_L2_PROMOTION_NONE, CU_TENSOR_MAP_FLOAT_OOB_FILL_NONE);
  }
  Params P;
  P.x = (const __nv_bfloat16*)d_in[0];
  P.wphi = (const __nv_bfloat16*)d_in[2];
  P.wo = (const __nv_bfloat16*)d_in[3];
  P.logA = (const __nv_bfloat16*)d_in[5];
  P.Aim = (const __nv_bfloat16*)d_in[6];
  P.Cre = (const __nv_bfloat16*)d_in[7];
  P.Cim = (const __nv_bfloat16*)d_in[8];
  P.logdt = (const __nv_bfloat16*)d_in[9];
  P.Dskip = (const __nv_bfloat16*)d_in[10];
  P.out = (__nv_bfloat16*)d_out;
  cudaGetSymbolAddress((void**)&P.xs, g_x);
  {
    cuuint64_t dims[3] = {1024, 2, 512}, st[2] = {U_ODD, U_CH};
    cuuint32_t box[3] = {64, 2, 64};
    enc(&mut, CU_TENSOR_MAP_DATA_TYPE_BFLOAT16, 3, P.xs + X_UT + U_PAD / 16, dims, st, box, es, CU_TENSOR_MAP_INTERLEAVE_NONE,
        CU_TENSOR_MAP_SWIZZLE_128B, CU_TENSOR_MAP_L2_PROMOTION_NONE, CU_TENSOR_MAP_FLOAT_OOB_FILL_NONE);
  }
  P.ts = nullptr;
  cudaFuncSetAttribute(fused_kernel, cudaFuncAttributeMaxDynamicSharedMemorySize, SMEM_BYTES);
  fused_kernel<<<NCTA, NTHREADS, SMEM_BYTES>>>(P, mx, mw, mo, mu, mout, mut);
}
```

```cpp
#include <cuda_runtime.h>
#include <cuda_bf16.h>
#include <cuda_fp16.h>
#include <cuda.h>
#include <stdint.h>
#include <type_traits>

#define DBG_TS 0

namespace {

constexpr int NTHREADS = 512;
constexpr int NCTA = 128;
constexpr int OFF_W = 0;
constexpr int OFF_X = 98304;
constexpr int OFF_U = OFF_X + 65536;
constexpr int U_CH = 4416, U_ODD = 2240, U_PAD = 128;
constexpr int OFF_STG0 = OFF_U + 18432;
constexpr int SLAB = 3328;
constexpr int OFF_T = OFF_STG0 + 8 * SLAB;
constexpr int T_CH = 5216;
constexpr int T_D = 0;
constexpr int T_5 = 2144;
constexpr int T_3 = T_5 + 384;
constexpr int T_7 = T_5 + 1024;
constexpr int T_9 = T_7 + 320;
constexpr int T_KC = T_9 + 320;
constexpr int T_ST = T_5 - 1024;
constexpr int OFF_PHI = OFF_T + 4 * T_CH;
constexpr int OFF_EYE = OFF_PHI + 1024, OFF_ONE = OFF_EYE + 512;
constexpr int OFF_BAR = OFF_ONE + 256;
constexpr int SMEM_BYTES = OFF_BAR + 512 + 256 * DBG_TS;
constexpr uint32_t SB = 1024;
static_assert(T_KC + 2 * 656 <= T_CH, "table size");
static_assert(SMEM_BYTES <= 232448, "smem");
constexpr int MB_URAW = 0, MB_FULL = 1  , MB_WO = 17, MB_UFULL = 18, MB_O = 19  ,
              MB_EMPTY = 23  , MB_AUX = 39;
__host__ __device__ constexpr uint32_t BAR(int i) { return SB + OFF_BAR + 8 * i; }
constexpr int NB_WG0 = 1, NB_ODONE = 2, NB_ST0 = 3, NB_HAND = 4, NB_KV = 5, NB_YZ = 6, NB_INIT = 7, NB_PREP = 8, NB_PROD = 9, NB_KREAD = 10,
              NB_BDONE = 11, NB_GATE = 12  , NB_Y = 7  ;
constexpr int U_AT = 2;
constexpr int ZERO_STEP = 12;
constexpr int SPIN_MAX = 1 << 16;

constexpr int X_CNT = 0;
constexpr int X_PART = 256;
constexpr int X_O = X_PART + 16 * 8 * 144;
constexpr int X_Y = X_O + 32 * 32 * 128;
constexpr int X_UT = X_Y + 512 * 8 * 32;
constexpr int X_SIZE = X_UT + 512 * (U_CH / 16);
__device__ __align__(128) uint4 g_x[X_SIZE];
extern __shared__ uint8_t smem_raw[];
#define TS(i) do {} while (0)
#define TS1(i) do {} while (0)
#define GT(i) do {} while (0)
#define TSDUMP(base) do {} while (0)

__device__ __forceinline__ uint32_t smem_u32(const void* p) { return (uint32_t)__cvta_generic_to_shared(p); }
__device__ __forceinline__ void mbar_arrive(uint32_t b) {
  asm volatile("mbarrier.arrive.shared::cta.b64 _, [%0];" ::"r"(b) : "memory");
}
__device__ __forceinline__ void mbar_wait(uint32_t b) {
  uint32_t done = 0;
#pragma unroll 1
  for (int i = 0; i < SPIN_MAX && !done; i++) {
    asm volatile("{\n.reg .pred p;\nmbarrier.try_wait.parity.shared::cta.b64 p, [%1], 0, 4000;\nselp.u32 %0, 1, 0, p;\n}\n"
                 : "=r"(done) : "r"(b) : "memory");
  }
}
__device__ __forceinline__ void mbar_spin(uint32_t b) {
  uint32_t done = 0;
#pragma unroll 1
  for (int i = 0; i < (SPIN_MAX << 4) && !done; i++) {
    asm volatile("{\n.reg .pred p;\nmbarrier.try_wait.parity.shared::cta.b64 p, [%1], 0;\nselp.u32 %0, 1, 0, p;\n}\n"
                 : "=r"(done) : "r"(b) : "memory");
  }
}
__device__ __forceinline__ void mbar_init(uint32_t b, int n) {
  asm volatile("mbarrier.init.shared::cta.b64 [%0], %1;" ::"r"(b), "r"(n) : "memory");
}
__device__ __forceinline__ void mbar_expect(uint32_t b, int bytes) {
  asm volatile("mbarrier.arrive.expect_tx.shared::cta.b64 _, [%0], %1;" ::"r"(b), "r"(bytes) : "memory");
}
__device__ __forceinline__ void nb_sync(int id, int n) { asm volatile("bar.sync %0, %1;" ::"r"(id), "r"(n) : "memory"); }
__device__ __forceinline__ void nb_arrive(int id, int n) { asm volatile("bar.arrive %0, %1;" ::"r"(id), "r"(n) : "memory"); }
#define ELECT "{\n.reg .pred p;\nelect.sync _|p, 0xffffffff;\n@p "
__device__ __forceinline__ void e_arrive(uint32_t b) {
  asm volatile(ELECT "mbarrier.arrive.shared::cta.b64 _, [%0];\n}\n" ::"r"(b) : "memory");
}
__device__ __forceinline__ void e_expect(uint32_t b, int bytes) {
  asm volatile(ELECT "mbarrier.arrive.expect_tx.shared::cta.b64 _, [%0], %1;\n}\n" ::"r"(b), "r"(bytes) : "memory");
}
__device__ __forceinline__ void e_tma2d(uint32_t dst, const CUtensorMap* m, uint32_t bar, int c0, int c1) {
  asm volatile(ELECT "cp.async.bulk.tensor.2d.shared::cluster.global.mbarrier::complete_tx::bytes [%0], [%1, {%3,%4}], [%2];\n}\n"
               ::"r"(dst), "l"(m), "r"(bar), "r"(c0), "r"(c1) : "memory");
}
__device__ __forceinline__ void e_tma3d(uint32_t dst, const CUtensorMap* m, uint32_t bar, int c0, int c1, int c2) {
  asm volatile(ELECT "cp.async.bulk.tensor.3d.shared::cluster.global.mbarrier::complete_tx::bytes [%0], [%1, {%3,%4,%5}], [%2];\n}\n"
               ::"r"(dst), "l"(m), "r"(bar), "r"(c0), "r"(c1), "r"(c2) : "memory");
}
__device__ __forceinline__ void e_tma4d(uint32_t dst, const CUtensorMap* m, uint32_t bar, int c0, int c3) {
  asm volatile(ELECT "cp.async.bulk.tensor.4d.shared::cluster.global.mbarrier::complete_tx::bytes [%0], [%1, {%3,%5,%5,%4}], [%2];\n}\n"
               ::"r"(dst), "l"(m), "r"(bar), "r"(c0), "r"(c3), "r"(0) : "memory");
}
__device__ __forceinline__ void e_bulk(uint32_t dst, const void* src, int bytes, uint32_t bar) {
  asm volatile(ELECT "cp.async.bulk.shared::cluster.global.mbarrier::complete_tx::bytes [%0], [%1], %2, [%3];\n}\n"
               ::"r"(dst), "l"(src), "r"(bytes), "r"(bar) : "memory");
}
__device__ __forceinline__ void e_prefetch(const void* p, int bytes) {
  asm volatile(ELECT "cp.async.bulk.prefetch.L2.global [%0], %1;\n}\n" ::"l"(p), "r"(bytes) : "memory");
}
__device__ __forceinline__ void e_store2d(const CUtensorMap* m, uint32_t src, int c0, int c1) {
  asm volatile(ELECT "cp.async.bulk.tensor.2d.global.shared::cta.bulk_group [%0, {%2,%3}], [%1];\n}\n"
               ::"l"(m), "r"(src), "r"(c0), "r"(c1) : "memory");
}
__host__ __device__ constexpr uint64_t mkdesc(uint32_t addr, uint32_t lbo, uint32_t sbo, int swz) {
  return (uint64_t)((addr & 0x3FFFF) >> 4) | ((uint64_t)(lbo >> 4) << 16) | ((uint64_t)(sbo >> 4) << 32) |
         ((uint64_t)swz << 62);
}
#define SPLIT() asm volatile("{\n.reg .pred p;\nsetp.eq.u32 p, %0, %1;\n@p exit;\n}\n" ::"r"(blockIdx.y), "n"(__LINE__) : "memory")
#define SPLITN(n) asm volatile("{\n.reg .pred p;\nsetp.eq.u32 p, %0, %1;\n@p exit;\n}\n" ::"r"(blockIdx.y), "r"(4096 + (n)) : "memory")
#define WG_FENCE() asm volatile("wgmma.fence.sync.aligned;" ::: "memory")
#define WG_COMMIT() asm volatile("wgmma.commit_group.sync.aligned;" ::: "memory")
#define WG_WAIT(n) asm volatile("wgmma.wait_group.sync.aligned " #n ";" ::: "memory")

__device__ __forceinline__ void mma(float& d0, float& d1, float& d2, float& d3, uint32_t a0, uint32_t a1, uint32_t a2,
                                    uint32_t a3, uint32_t b0, uint32_t b1) {
  asm volatile("mma.sync.aligned.m16n8k16.row.col.f32.bf16.bf16.f32 {%0,%1,%2,%3},{%4,%5,%6,%7},{%8,%9},{%0,%1,%2,%3};"
               : "+f"(d0), "+f"(d1), "+f"(d2), "+f"(d3)
               : "r"(a0), "r"(a1), "r"(a2), "r"(a3), "r"(b0), "r"(b1));
}
__device__ __forceinline__ void mmac(float (&d)[4], uint32_t a0, uint32_t a1, uint32_t a2, uint32_t a3, uint32_t b0,
                                     uint32_t b1, const float (&c)[4]) {
  asm volatile("mma.sync.aligned.m16n8k16.row.col.f32.bf16.bf16.f32 {%0,%1,%2,%3},{%4,%5,%6,%7},{%8,%9},{%10,%11,%12,%13};"
               : "=f"(d[0]), "=f"(d[1]), "=f"(d[2]), "=f"(d[3])
               : "r"(a0), "r"(a1), "r"(a2), "r"(a3), "r"(b0), "r"(b1), "f"(c[0]), "f"(c[1]), "f"(c[2]), "f"(c[3]));
}
__device__ __forceinline__ void mma_h(float (&d)[4], const uint32_t (&a)[4], uint32_t b0, uint32_t b1) {
  asm volatile("mma.sync.aligned.m16n8k16.row.col.f32.f16.f16.f32 {%0,%1,%2,%3},{%4,%5,%6,%7},{%8,%9},{%0,%1,%2,%3};"
               : "+f"(d[0]), "+f"(d[1]), "+f"(d[2]), "+f"(d[3]) : "r"(a[0]), "r"(a[1]), "r"(a[2]), "r"(a[3]), "r"(b0), "r"(b1));
}
__device__ __forceinline__ void mma0(float& d0, float& d1, float& d2, float& d3, uint32_t a0, uint32_t a1, uint32_t a2,
                                     uint32_t a3, uint32_t b0, uint32_t b1) {
  asm volatile("mma.sync.aligned.m16n8k16.row.col.f32.bf16.bf16.f32 {%0,%1,%2,%3},{%4,%5,%6,%7},{%8,%9},{%10,%10,%10,%10};"
               : "=f"(d0), "=f"(d1), "=f"(d2), "=f"(d3)
               : "r"(a0), "r"(a1), "r"(a2), "r"(a3), "r"(b0), "r"(b1), "f"(0.f));
}
__device__ __forceinline__ uint32_t pack_bf(float lo, float hi) {
  uint32_t r;
  asm("cvt.rn.bf16x2.f32 %0, %1, %2;" : "=r"(r) : "f"(hi), "f"(lo));
  return r;
}
__device__ __forceinline__ float bf_lo(uint32_t w) { return __uint_as_float(w << 16); }
__device__ __forceinline__ float bf_hi(uint32_t w) { return __uint_as_float(w & 0xffff0000u); }
__device__ __forceinline__ float bf_round(float x) { return __bfloat162float(__float2bfloat16_rn(x)); }
__device__ __forceinline__ uint32_t bmax2(uint32_t a, uint32_t b) {
  uint32_t r; asm("max.bf16x2 %0, %1, %2;" : "=r"(r) : "r"(a), "r"(b)); return r;
}
__device__ __forceinline__ uint32_t bmin2(uint32_t a, uint32_t b) {
  uint32_t r; asm("min.bf16x2 %0, %1, %2;" : "=r"(r) : "r"(a), "r"(b)); return r;
}
__device__ __forceinline__ float ex2(float x) { float r; asm("ex2.approx.ftz.f32 %0, %1;" : "=f"(r) : "f"(x)); return r; }
__device__ __forceinline__ float rcp(float x) { float r; asm("rcp.approx.ftz.f32 %0, %1;" : "=f"(r) : "f"(x)); return r; }
__device__ __forceinline__ void ldsm4(uint32_t (&r)[4], uint32_t a) {
  asm volatile("ldmatrix.sync.aligned.m8n8.x4.shared.b16 {%0,%1,%2,%3}, [%4];"
               : "=r"(r[0]), "=r"(r[1]), "=r"(r[2]), "=r"(r[3]) : "r"(a) : "memory");
}
__device__ __forceinline__ void ldsm4t(uint32_t (&r)[4], uint32_t a) {
  asm volatile("ldmatrix.sync.aligned.m8n8.x4.trans.shared.b16 {%0,%1,%2,%3}, [%4];"
               : "=r"(r[0]), "=r"(r[1]), "=r"(r[2]), "=r"(r[3]) : "r"(a) : "memory");
}
__device__ __forceinline__ void stsm4(uint32_t a, uint32_t r0, uint32_t r1, uint32_t r2, uint32_t r3) {
  asm volatile("stmatrix.sync.aligned.m8n8.x4.shared.b16 [%0], {%1,%2,%3,%4};"
               ::"r"(a), "r"(r0), "r"(r1), "r"(r2), "r"(r3) : "memory");
}
__device__ __forceinline__ uint32_t lds32(uint32_t a) {
  uint32_t r; asm volatile("ld.shared.u32 %0, [%1];" : "=r"(r) : "r"(a) : "memory"); return r;
}
__device__ __forceinline__ uint32_t lds16(uint32_t a) {
  uint32_t r; asm volatile("{\n.reg .u16 h;\nld.shared.u16 h, [%1];\ncvt.u32.u16 %0, h;\n}\n" : "=r"(r) : "r"(a) : "memory"); return r;
}
__device__ __forceinline__ uint2 lds64(uint32_t a) {
  uint2 r; asm volatile("ld.shared.v2.u32 {%0,%1}, [%2];" : "=r"(r.x), "=r"(r.y) : "r"(a) : "memory"); return r;
}
__device__ __forceinline__ uint4 lds128(uint32_t a) {
  uint4 r;
  asm volatile("ld.shared.v4.u32 {%0,%1,%2,%3}, [%4];" : "=r"(r.x), "=r"(r.y), "=r"(r.z), "=r"(r.w) : "r"(a) : "memory");
  return r;
}
__device__ __forceinline__ void sts32(uint32_t a, uint32_t v) { asm volatile("st.shared.u32 [%0], %1;" ::"r"(a), "r"(v) : "memory"); }
__device__ __forceinline__ void sts16(uint32_t a, uint32_t v) {
  asm volatile("{\n.reg .u16 h;\ncvt.u16.u32 h, %1;\nst.shared.u16 [%0], h;\n}\n" ::"r"(a), "r"(v) : "memory");
}
__device__ __forceinline__ void sts64(uint32_t a, uint32_t x, uint32_t y) {
  asm volatile("st.shared.v2.u32 [%0], {%1,%2};" ::"r"(a), "r"(x), "r"(y) : "memory");
}
__device__ __forceinline__ void sts128(uint32_t a, uint32_t x, uint32_t y, uint32_t z, uint32_t w) {
  asm volatile("st.shared.v4.u32 [%0], {%1,%2,%3,%4};" ::"r"(a), "r"(x), "r"(y), "r"(z), "r"(w) : "memory");
}
__device__ __forceinline__ uint4 ld_x(const uint4* p) {
  uint4 r;
  asm volatile("{\n.reg .b128 t;\nld.relaxed.gpu.global.b128 t, [%4];\nmov.b128 {%0,%1,%2,%3}, t;\n}\n"
               : "=r"(r.x), "=r"(r.y), "=r"(r.z), "=r"(r.w) : "l"(p) : "memory");
  return r;
}
__device__ __forceinline__ uint32_t ld_x32(const uint32_t* p) {
  uint32_t r; asm volatile("ld.relaxed.gpu.global.u32 %0, [%1];" : "=r"(r) : "l"(p) : "memory"); return r;
}
__device__ __forceinline__ void st_x(uint4* p, uint32_t x, uint32_t y, uint32_t z, uint32_t w) {
  asm volatile("{\n.reg .b128 t;\nmov.b128 t, {%1,%2,%3,%4};\nst.relaxed.gpu.global.b128 [%0], t;\n}\n"
               ::"l"(p), "r"(x), "r"(y), "r"(z), "r"(w) : "memory");
}
__device__ __forceinline__ void st_x32(uint32_t* p, uint32_t x) {
  asm volatile("st.relaxed.gpu.global.u32 [%0], %1;" ::"l"(p), "r"(x) : "memory");
}
__device__ __forceinline__ uint32_t nz(uint32_t w) { return max(w, 1u); }
__device__ __forceinline__ uint32_t fu(float x) { return __float_as_uint(x); }
__device__ __forceinline__ float uf(uint32_t x) { return __uint_as_float(x); }

__device__ __forceinline__ void wgmma_ss_n96(float (&d)[48], uint64_t da, uint64_t db, int sc) {
  asm volatile("{\n.reg .pred p;\nsetp.ne.b32 p, %50, 0;\n"
      "wgmma.mma_async.sync.aligned.m64n96k16.f32.bf16.bf16 "
      "{%0,%1,%2,%3,%4,%5,%6,%7,%8,%9,%10,%11,%12,%13,%14,%15,%16,%17,%18,%19,%20,%21,%22,%23,%24,%25,%26,%27,%28,%29,%30,%31,%32,%33,%34,%35,%36,%37,%38,%39,%40,%41,%42,%43,%44,%45,%46,%47}, "
      "%48, %49, p, 1, 1, 0, 1;\n}\n"
      : "+f"(d[0]), "+f"(d[1]), "+f"(d[2]), "+f"(d[3]), "+f"(d[4]), "+f"(d[5]), "+f"(d[6]), "+f"(d[7]),
        "+f"(d[8]), "+f"(d[9]), "+f"(d[10]), "+f"(d[11]), "+f"(d[12]), "+f"(d[13]), "+f"(d[14]), "+f"(d[15]),
        "+f"(d[16]), "+f"(d[17]), "+f"(d[18]), "+f"(d[19]), "+f"(d[20]), "+f"(d[21]), "+f"(d[22]), "+f"(d[23]),
        "+f"(d[24]), "+f"(d[25]), "+f"(d[26]), "+f"(d[27]), "+f"(d[28]), "+f"(d[29]), "+f"(d[30]), "+f"(d[31]),
        "+f"(d[32]), "+f"(d[33]), "+f"(d[34]), "+f"(d[35]), "+f"(d[36]), "+f"(d[37]), "+f"(d[38]), "+f"(d[39]),
        "+f"(d[40]), "+f"(d[41]), "+f"(d[42]), "+f"(d[43]), "+f"(d[44]), "+f"(d[45]), "+f"(d[46]), "+f"(d[47])
      : "l"(da), "l"(db), "r"(sc));
}

__device__ __forceinline__ void wgmma_ss_n128(float (&d)[64], uint64_t da, uint64_t db, int sc) {
  asm volatile("{\n.reg .pred p;\nsetp.ne.b32 p, %66, 0;\n"
      "wgmma.mma_async.sync.aligned.m64n128k16.f32.bf16.bf16 "
      "{%0,%1,%2,%3,%4,%5,%6,%7,%8,%9,%10,%11,%12,%13,%14,%15,%16,%17,%18,%19,%20,%21,%22,%23,%24,%25,%26,%27,%28,%29,%30,%31,%32,%33,%34,%35,%36,%37,%38,%39,%40,%41,%42,%43,%44,%45,%46,%47,%48,%49,%50,%51,%52,%53,%54,%55,%56,%57,%58,%59,%60,%61,%62,%63}, "
      "%64, %65, p, 1, 1, 0, 1;\n}\n"
      : "+f"(d[0]), "+f"(d[1]), "+f"(d[2]), "+f"(d[3]), "+f"(d[4]), "+f"(d[5]), "+f"(d[6]), "+f"(d[7]),
        "+f"(d[8]), "+f"(d[9]), "+f"(d[10]), "+f"(d[11]), "+f"(d[12]), "+f"(d[13]), "+f"(d[14]), "+f"(d[15]),
        "+f"(d[16]), "+f"(d[17]), "+f"(d[18]), "+f"(d[19]), "+f"(d[20]), "+f"(d[21]), "+f"(d[22]), "+f"(d[23]),
        "+f"(d[24]), "+f"(d[25]), "+f"(d[26]), "+f"(d[27]), "+f"(d[28]), "+f"(d[29]), "+f"(d[30]), "+f"(d[31]),
        "+f"(d[32]), "+f"(d[33]), "+f"(d[34]), "+f"(d[35]), "+f"(d[36]), "+f"(d[37]), "+f"(d[38]), "+f"(d[39]),
        "+f"(d[40]), "+f"(d[41]), "+f"(d[42]), "+f"(d[43]), "+f"(d[44]), "+f"(d[45]), "+f"(d[46]), "+f"(d[47]),
        "+f"(d[48]), "+f"(d[49]), "+f"(d[50]), "+f"(d[51]), "+f"(d[52]), "+f"(d[53]), "+f"(d[54]), "+f"(d[55]),
        "+f"(d[56]), "+f"(d[57]), "+f"(d[58]), "+f"(d[59]), "+f"(d[60]), "+f"(d[61]), "+f"(d[62]), "+f"(d[63])
      : "l"(da), "l"(db), "r"(sc));
}

__device__ __forceinline__ void wgmma_ss_n40(float (&d)[20], uint64_t da, uint64_t db, int sc) {
  asm volatile("{\n.reg .pred p;\nsetp.ne.b32 p, %22, 0;\n"
      "wgmma.mma_async.sync.aligned.m64n40k16.f32.bf16.bf16 "
      "{%0,%1,%2,%3,%4,%5,%6,%7,%8,%9,%10,%11,%12,%13,%14,%15,%16,%17,%18,%19}, "
      "%20, %21, p, 1, 1, 1, 1;\n}\n"
      : "+f"(d[0]), "+f"(d[1]), "+f"(d[2]), "+f"(d[3]), "+f"(d[4]), "+f"(d[5]), "+f"(d[6]), "+f"(d[7]),
        "+f"(d[8]), "+f"(d[9]), "+f"(d[10]), "+f"(d[11]), "+f"(d[12]), "+f"(d[13]), "+f"(d[14]), "+f"(d[15]),
        "+f"(d[16]), "+f"(d[17]), "+f"(d[18]), "+f"(d[19])
      : "l"(da), "l"(db), "r"(sc));
}

__device__ __forceinline__ void wgmma_rs_n8(float (&d)[4], const uint4& a, uint64_t db, int sc) {
  asm volatile("{\n.reg .pred p;\nsetp.ne.b32 p, %9, 0;\n"
      "wgmma.mma_async.sync.aligned.m64n8k16.f32.bf16.bf16 "
      "{%0,%1,%2,%3}, "
      "{%4,%5,%6,%7}, %8, p, 1, 1, 1;\n}\n"
      : "+f"(d[0]), "+f"(d[1]), "+f"(d[2]), "+f"(d[3])
      : "r"(a.x), "r"(a.y), "r"(a.z), "r"(a.w), "l"(db), "r"(sc));
}

__device__ __forceinline__ void wgmma_rs_n16(float (&d)[8], const uint4& a, uint64_t db, int sc) {
  asm volatile("{\n.reg .pred p;\nsetp.ne.b32 p, %13, 0;\n"
      "wgmma.mma_async.sync.aligned.m64n16k16.f32.bf16.bf16 "
      "{%0,%1,%2,%3,%4,%5,%6,%7}, "
      "{%8,%9,%10,%11}, %12, p, 1, 1, 1;\n}\n"
      : "+f"(d[0]), "+f"(d[1]), "+f"(d[2]), "+f"(d[3]), "+f"(d[4]), "+f"(d[5]), "+f"(d[6]), "+f"(d[7])
      : "r"(a.x), "r"(a.y), "r"(a.z), "r"(a.w), "l"(db), "r"(sc));
}

__device__ __forceinline__ void wgmma_rs_n24(float (&d)[12], const uint4& a, uint64_t db, int sc) {
  asm volatile("{\n.reg .pred p;\nsetp.ne.b32 p, %17, 0;\n"
      "wgmma.mma_async.sync.aligned.m64n24k16.f32.bf16.bf16 "
      "{%0,%1,%2,%3,%4,%5,%6,%7,%8,%9,%10,%11}, "
      "{%12,%13,%14,%15}, %16, p, 1, 1, 1;\n}\n"
      : "+f"(d[0]), "+f"(d[1]), "+f"(d[2]), "+f"(d[3]), "+f"(d[4]), "+f"(d[5]), "+f"(d[6]), "+f"(d[7]),
        "+f"(d[8]), "+f"(d[9]), "+f"(d[10]), "+f"(d[11])
      : "r"(a.x), "r"(a.y), "r"(a.z), "r"(a.w), "l"(db), "r"(sc));
}

struct Params {
  const __nv_bfloat16 *logA, *Aim, *Cre, *Cim, *logdt, *Dskip, *x, *wphi, *wo;
  __nv_bfloat16* out;
  uint4* xs;
  long long* ts;
};

__device__ __forceinline__ uint4 tr_row(const uint4 (&v)[8], int i) {
  uint32_t o[4];
#pragma unroll
  for (int m = 0; m < 4; m++) {
    const uint4 &ra = v[2 * m], &rb = v[2 * m + 1];
    const int k = i >> 1;
    const uint32_t xa = k == 0 ? ra.x : k == 1 ? ra.y : k == 2 ? ra.z : ra.w;
    const uint32_t xb = k == 0 ? rb.x : k == 1 ? rb.y : k == 2 ? rb.z : rb.w;
    o[m] = __byte_perm(xa, xb, (i & 1) ? 0x7632 : 0x5410);
  }
  return make_uint4(o[0], o[1], o[2], o[3]);
}

struct cpx { float r, i; };
__device__ __forceinline__ cpx csq(cpx a) { return {a.r * a.r - a.i * a.i, 2.f * (a.r * a.i)}; }
__device__ __forceinline__ cpx polar(float e, float t) {
  const float m = ex2(e);
  return {m * __cosf(t), m * __sinf(t)};
}

struct KgenRaw { uint32_t la, ai, cr, ci, ldt; };
__device__ __forceinline__ KgenRaw kgen_load(const Params& P, int d, int unit, int lane, int on) {
  const int o = d * 64 + unit * 32 + lane;
  KgenRaw r = {0, 0, 0, 0, 0};
  asm volatile("{\n.reg .pred p;\nsetp.ne.b32 p, %10, 0;\n@p ld.global.nc.u32 %0, [%5];\n@p ld.global.nc.u32 %1, [%6];\n"
               "@p ld.global.nc.u32 %2, [%7];\n@p ld.global.nc.u32 %3, [%8];\n@p ld.global.nc.u16 %4, [%9];\n}\n"
               : "+r"(r.la), "+r"(r.ai), "+r"(r.cr), "+r"(r.ci), "+r"(r.ldt)
               : "l"((const uint32_t*)P.logA + o), "l"((const uint32_t*)P.Aim + o), "l"((const uint32_t*)P.Cre + o),
                 "l"((const uint32_t*)P.Cim + o), "l"(P.logdt + d), "r"(on));
  return r;
}
struct hc { __half2 r, i; };
struct cpx2 { cpx a, b; };
__device__ __forceinline__ cpx2 csq2(const cpx2& v) { return {csq(v.a), csq(v.b)}; }
__device__ __forceinline__ hc toh(const cpx2& v) { return {__floats2half2_rn(v.a.r, v.b.r), __floats2half2_rn(v.a.i, v.b.i)}; }
__device__ __forceinline__ hc hmul(const hc& z, const hc& w) {
  return {__hfma2(z.r, w.r, __hneg2(__hmul2(z.i, w.i))), __hfma2(z.r, w.i, __hmul2(z.i, w.r))};
}
__device__ __forceinline__ hc hmulc(const hc& z, const hc& w) {
  return {__hfma2(z.r, w.r, __hmul2(z.i, w.i)), __hfma2(z.i, w.r, __hneg2(__hmul2(z.r, w.i)))};
}
__device__ __forceinline__ uint32_t hu(__half2 v) { return *(const uint32_t*)&v; }
__device__ __forceinline__ __half2 uh(uint32_t v) { return *(const __half2*)&v; }

struct KgenAddr { uint32_t sa[2], ld[5][4]; };
__device__ __forceinline__ KgenAddr kgen_addr(int lane, uint32_t buf) {
  KgenAddr a;
  a.sa[0] = buf + (lane & 7) * 128 + ((((lane >> 3) ^ lane) & 7) << 4);
  a.sa[1] = a.sa[0] ^ 64;
  const int q = lane >> 4;
  const uint32_t b = buf + ((lane >> 3) & 1) * 1024 + q * 128;
  const int e[5] = {lane & 7, 0, 1, 2 + (lane & 1), 4 + (lane & 3)};
#pragma unroll
  for (int i = 0; i < 20; i++) {
    a.ld[i >> 2][i & 3] = b + ((e[i >> 2] ^ q ^ (2 * (i & 3))) << 4);
    asm volatile("" : "+r"(a.ld[i >> 2][i & 3]));
  }
  asm volatile("" : "+r"(a.sa[0]), "+r"(a.sa[1]));
  return a;
}
__device__ __forceinline__ void kgen_unit(const KgenRaw& r, const KgenAddr& ad, uint32_t zero, float (&k)[5][4], float& k2048, float& sc) {
  const float dt = bf_round(expf(bf_lo(r.ldt)));
  const uint32_t ar = pack_bf(ex2(bf_lo(r.la) * 1.4426950408889634f), ex2(bf_hi(r.la) * 1.4426950408889634f));
  const float ca = dt * -1.4426950408889634f, a0 = bf_lo(ar) * ca, a1 = bf_hi(ar) * ca;
  const float f0 = bf_lo(r.ai) * dt, f1 = bf_hi(r.ai) * dt;
  const float r0 = f0 * 20.21267777267071f, r1 = f1 * 20.21267777267071f;
  const uint32_t cm = __vmaxu2(r.cr & 0x7fff7fffu, r.ci & 0x7fff7fffu);
  const uint32_t ex = min(max(__reduce_max_sync(0xffffffffu, max(cm >> 16, cm & 0xffffu)) >> 7, 1u), 253u);
  const float cs = uf((254u - ex) << 23);
  sc = 2.f * dt * uf(ex << 23);
  const cpx2 C = {{bf_lo(r.cr) * cs, bf_lo(r.ci) * -cs}, {bf_hi(r.cr) * cs, bf_hi(r.ci) * -cs}};
  auto put = [&](const hc (&v)[8]) {
    stsm4(ad.sa[0], hu(v[0].r), hu(v[1].r), hu(v[2].r), hu(v[3].r));
    stsm4(ad.sa[0] + 1024, hu(v[0].i), hu(v[1].i), hu(v[2].i), hu(v[3].i));
    stsm4(ad.sa[1], hu(v[4].r), hu(v[5].r), hu(v[6].r), hu(v[7].r));
    stsm4(ad.sa[1] + 1024, hu(v[4].i), hu(v[5].i), hu(v[6].i), hu(v[7].i));
    __syncwarp();
  };
  auto get = [&](uint32_t (&o)[4][4], const uint32_t (&a)[4]) {
#pragma unroll
    for (int i = 0; i < 4; i++) ldsm4(o[i], a[i] + i * 256);
  };
  auto at = [](const uint32_t (&o)[4][4], int s) { return hc{uh(o[s >> 1][2 * (s & 1)]), uh(o[s >> 1][2 * (s & 1) + 1])}; };
  uint32_t A[8][4];
  auto tile = [&](int j, const uint32_t (&B)[4][4]) {
    k[j][0] = k[j][1] = k[j][2] = k[j][3] = 0.f;
#pragma unroll
    for (int s = 0; s < 8; s++) mma_h(k[j], A[s], B[s >> 1][2 * (s & 1)], B[s >> 1][2 * (s & 1) + 1]);
  };
  const cpx2 w1 = {polar(a0, f0), polar(a1, f1)};
  const cpx2 w127 = {polar(a0 * 127.f, (r0 - rintf(r0)) * 6.283185307179586f), polar(a1 * 127.f, (r1 - rintf(r1)) * 6.283185307179586f)};
  const cpx2 w2 = csq2(w1), w4 = csq2(w2);
  uint32_t T0[4][4], X[4][4], M[3][4][4];
  {
    hc t[8];
    t[0] = {uh(0x3C003C00u), uh(0u)}; t[1] = toh(w1); t[2] = toh(w2); t[4] = toh(w4);
    t[3] = hmul(t[1], t[2]); t[5] = hmul(t[1], t[4]); t[6] = hmul(t[2], t[4]); t[7] = hmul(t[3], t[4]);
    put(t); get(T0, ad.ld[0]);
  }
  SPLIT();
  const cpx2 w8 = csq2(w4), w16 = csq2(w8), w32 = csq2(w16), w64 = csq2(w32);
  {
    const hc m8 = toh(w8), m16 = toh(w16), m32 = toh(w32);
    hc a[8];
    a[0] = toh(C); a[1] = hmulc(a[0], m8);
    a[2] = hmulc(a[0], m16); a[3] = hmulc(a[1], m16);
#pragma unroll
    for (int i = 0; i < 4; i++) a[4 + i] = hmulc(a[i], m32);
    put(a); get(X, ad.ld[0]);
  }
  SPLIT();
    const cpx2 w128 = {{w127.a.r * w1.a.r - w127.a.i * w1.a.i, w127.a.r * w1.a.i + w127.a.i * w1.a.r},
                     {w127.b.r * w1.b.r - w127.b.i * w1.b.i, w127.b.r * w1.b.i + w127.b.i * w1.b.r}};
  const cpx2 w256 = csq2(w128), w512 = csq2(w256);
  const hc m128 = toh(w128), m256 = toh(w256), m512 = toh(w512);
  {
    const hc m254 = toh(csq2(w127)), m127 = toh(w127);
    hc m[8];
    m[0] = toh(w64); m[1] = m128; m[2] = m256; m[3] = hmul(m127, m256);
    m[4] = m512; m[5] = hmul(m127, m512); m[6] = hmul(m[4], m254); m[7] = hmul(m[5], m254);
    put(m);
    get(M[0], ad.ld[1]);
#pragma unroll
    for (int s = 0; s < 8; s++) {
      const hc z = at(X, s), y = hmulc(z, at(M[0], s));
      A[s][0] = hu(z.r) + zero; A[s][1] = hu(y.r); A[s][2] = hu(z.i) + zero; A[s][3] = hu(y.i);
    }
#pragma unroll
    for (int i = 0; i < 3; i++) get(M[i], ad.ld[i + 2]);
  }
  SPLIT();
  tile(0, T0);
  const cpx2 w1024 = csq2(w512), we = csq2(w1024);
  {
    hc t[8];
    t[0] = toh(w1024); t[1] = hmul(t[0], m128);
    t[2] = hmul(t[0], m256); t[3] = hmul(t[1], m256);
#pragma unroll
    for (int i = 0; i < 4; i++) t[4 + i] = hmul(t[i], m512);
    put(t); get(X, ad.ld[0]);
  }
  k2048 = (C.a.r * we.a.r + C.a.i * we.a.i + C.b.r * we.b.r + C.b.i * we.b.i) * sc;
#pragma unroll
  for (int j = 1; j < 5; j++) k[j][0] = k[j][1] = k[j][2] = k[j][3] = 0.f;
#pragma unroll
  for (int s = 0; s < 8; s++) {
#pragma unroll
    for (int j = 0; j < 3; j++) {
      const hc y = hmul(at(T0, s), at(M[j], s));
      mma_h(k[1 + j], A[s], hu(y.r), hu(y.i));
    }
    mma_h(k[4], A[s], X[s >> 1][2 * (s & 1)], X[s >> 1][2 * (s & 1) + 1]);
  }
}

__device__ __forceinline__ void build_tables(uint32_t tb, int lane, float (&k)[5][4], float k2048) {
  const int g = lane >> 2, c = lane & 3;
  const uint32_t kc = tb + T_KC + 16;
  {
    const uint32_t a0 = kc + 16 * g + 4 * c, a2 = kc + 2 * (256 + 4 * g + c);
    const uint32_t a3 = kc + 2 * (384 + 2 * g + 64 * (c & 1) + (c >> 1)), a4 = kc + 2 * (512 + g + 32 * c);
#pragma unroll
    for (int r = 0; r < 2; r++) {
      sts32(a0 + 128 * r, pack_bf(k[0][2 * r], k[0][2 * r + 1]));
      sts32(a0 + 128 * r + 256, pack_bf(k[1][2 * r], k[1][2 * r + 1]));
      const uint32_t w2 = pack_bf(k[2][2 * r], k[2][2 * r + 1]);
      const uint32_t w3 = pack_bf(k[3][2 * r], k[3][2 * r + 1]);
      const uint32_t w4 = pack_bf(k[4][2 * r], k[4][2 * r + 1]);
      sts16(a2 + 64 * r, w2); sts16(a2 + 64 * r + 128, w2 >> 16);
      sts16(a3 + 32 * r, w3); sts16(a3 + 32 * r + 64, w3 >> 16);
      sts16(a4 + 16 * r, w4); sts16(a4 + 16 * r + 32, w4 >> 16);
    }
  }
  if (lane == 0) { sts16(kc + 2 * 640, pack_bf(k2048, 0.f)); sts32(kc - 4, 0); }
  __syncwarp();
  const uint32_t td = tb + T_D + 32;
#pragma unroll
  for (int hf = 0; hf < 2; hf++) {
    const uint2 v = lds64(kc + 256 * hf + 8 * lane);
    const uint32_t pv = lds32(kc + 256 * hf + 8 * lane - 4);
    sts128(td + 512 * hf + 16 * lane, __byte_perm(v.x, pv, 0x7610), __byte_perm(v.x, v.x, 0x1032), __byte_perm(v.y, v.x, 0x7610),
           __byte_perm(v.y, v.y, 0x1032));
  }
#pragma unroll
  for (int hf = 0; hf < 2; hf++) {
    const uint32_t v = lds32(kc + 512 + 128 * hf + 4 * lane), nx = lds32(kc + 516 + 128 * hf + 4 * lane);
    uint32_t w0 = __byte_perm(v, v, 0x1010);
    const uint32_t w1 = w0;
    if (hf == 0) { const uint32_t pv = lds32(kc + 508); if (lane == 0) w0 = __byte_perm(v, pv, 0x7610); }
    sts128(td + 1024 + 512 * hf + 16 * lane, w0, w1, __byte_perm(v, v, 0x1032), __byte_perm(nx, v, 0x7610));
  }
  {
    const uint32_t kk = lds16(kc + 2 * 384);
    const uint32_t w = lane < 3 ? (kk | (kk << 16)) : (lane == 3 ? (kk << 16) : 0u);
    if (lane < 24) sts32(td + 4 * (lane < 16 ? 512 + lane : lane - 24), w);
    const uint32_t lo_ = lds16(kc + 2 * 511), le_ = lds16(kc + 2 * 512);
    const uint32_t ja = tb + T_5 + (lane < 16 ? 4 * lane : 256 + 4 * lane);
    sts32(ja, lane == 16 ? (le_ << 16) : 0u);
    sts32(ja + 384, lane == 16 ? (lo_ << 16) : 0u);
    sts32(tb + (lane < 16 ? T_7 : T_9 - 64) + 4 * lane, 0u);
  }
#pragma unroll
  for (int s = 0; s < 2; s++) {
    const uint32_t b = kc + 2 * (s ? 512 : 384) + 8 * lane;
    const uint2 v = lds64(b);
    uint32_t em = lds16(b - 2), e0 = v.x;
    const uint32_t e4 = lds16(b + 8);
    if (lane == 0) { em = 0; e0 = 0; }
    sts64(tb + (s ? T_7 : T_3) + 64 + 8 * lane, __byte_perm(v.x, em, 0x5432), __byte_perm(v.y, v.x, 0x7632));
    sts64(tb + (s ? T_9 : T_5) + 64 + 8 * lane, __byte_perm(v.y, e0, 0x5410), __byte_perm(e4, v.y, 0x5410));
  }
  __syncwarp();
}

__device__ __forceinline__ uint32_t box2w(int lo, int n, int o) {
  return ((unsigned)(o - lo) < (unsigned)n ? 0x3F80u : 0u) | ((unsigned)(o + 1 - lo) < (unsigned)n ? 0x3F800000u : 0u);
}

__device__ __forceinline__ void conv_channel(uint32_t ub, uint32_t tb, int lane, uint4* ydst) {
  const int g = lane >> 2, c = lane & 3, x = g - 2 * c;
  const int mi = lane >> 3;
  const uint32_t qa = ub + U_PAD + 16 * (lane & 7) + ((mi == 0 || mi == 3) ? U_ODD : 0) - (mi == 0 ? 16 : 0);
  const uint32_t hb = ub + U_PAD + (mi & 1) * U_ODD + 16 * ((lane >> 4) + (lane & 7)) - 16;
  const uint32_t kv = lds16(tb + T_KC + 16 + 2 * 512);
  const int oh = c < 2 ? 8 + 2 * c : 2 * c - 8, og = c < 3 ? 2 * c : -10;
  uint32_t bx[4] = {box2w(g - 4, 9, 2 * c), box2w(g - 3, 7, 2 * c), box2w(g - 4, 9, oh), box2w(g - 3, 7, oh)};
  uint32_t by[4] = {box2w(g - 10, 5, 2 * c - 8), box2w(g - 5, 3, 2 * c - 8), box2w(g - 10, 5, og), box2w(g - 5, 3, og)};
  uint32_t lb0 = ((unsigned)(x + 5) < 2u ? kv : 0u) | ((unsigned)(x + 4) < 2u ? kv << 16 : 0u);
  uint32_t lb1 = ((unsigned)(x - 3) < 2u ? kv : 0u) | ((unsigned)(x - 4) < 2u ? kv << 16 : 0u);
  const int q0 = g - 1, q1 = c < 3 ? g : g - 2;
  uint32_t y0a = ub + U_PAD + (q0 & 1) * U_ODD + 16 * (q0 >> 1) + 4 * c;
  uint32_t y1a = ub + U_PAD + (q1 & 1) * U_ODD + 16 * (q1 >> 1) + 4 * c;
#pragma unroll
  for (int i = 0; i < 4; i++) asm volatile("" : "+r"(bx[i]), "+r"(by[i]));
  asm volatile("" : "+r"(lb0), "+r"(lb1), "+r"(y0a), "+r"(y1a));
  mbar_wait(BAR(MB_UFULL));
  mbar_spin(BAR(MB_EMPTY + 15));
  TS(36);
  float acc[16][4];
  {
    uint32_t z09[8], z07[8], zm9[8], zm7[8];
#pragma unroll
    for (int i = 0; i < 8; i++) {
      uint32_t h[4];
      ldsm4(h, hb + 128 * i);
      float y0, y1, y2, y3, w0, w1, w2, w3;
      mma0(y0, y1, y2, y3, bx[0], bx[1], bx[2], bx[3], h[2], c < 2 ? h[3] : h[1]);
      mma0(w0, w1, w2, w3, bx[0], bx[1], bx[2], bx[3], h[1], c < 2 ? h[2] : h[0]);
      z09[i] = pack_bf(y0, y1); z07[i] = pack_bf(y2, y3);
      zm9[i] = pack_bf(w0, w1); zm7[i] = pack_bf(w2, w3);
    }
  uint32_t f3[3][4][4];
  {
    const uint32_t fa = tb + T_7 + 4 * (16 + x);
#pragma unroll
    for (int tt = 0; tt < 3; tt++)
#pragma unroll
      for (int D = 0; D < 4; D++) {
        const uint32_t a = fa + (tt == 0 ? 316 : (tt == 1 ? 320 : 0)) + 64 * D;
        f3[tt][D][0] = lds32(a); f3[tt][D][1] = lds32(a + 32); f3[tt][D][2] = lds32(a - 32); f3[tt][D][3] = lds32(a);
      }
  }
    SPLIT();
    nb_sync(NB_GATE, 256);
    SPLIT();
    float a[4][2][4];
#pragma unroll
    for (int kap = 0; kap < 4; kap++)
#pragma unroll
      for (int sg = 0; sg < 2; sg++)
#pragma unroll
        for (int bk = 3; bk >= kap; bk--) {
          const uint32_t(&q0_)[4] = f3[sg ? 2 : 0][bk - kap];
          const uint32_t(&q1_)[4] = f3[sg ? 2 : 1][bk - kap];
          float(&a0)[4] = a[bk][0];
          float(&a1)[4] = a[bk][1];
          if (sg == 0 && kap == 0) {
            mma0(a0[0], a0[1], a0[2], a0[3], q0_[0], q0_[1], q0_[2], q0_[3], z09[0], z09[1]);
            mma0(a1[0], a1[1], a1[2], a1[3], q1_[0], q1_[1], q1_[2], q1_[3], zm9[0], zm9[1]);
          } else {
            mma(a0[0], a0[1], a0[2], a0[3], q0_[0], q0_[1], q0_[2], q0_[3], sg ? zm7[2 * kap] : z09[2 * kap], sg ? zm7[2 * kap + 1] : z09[2 * kap + 1]);
            mma(a1[0], a1[1], a1[2], a1[3], q1_[0], q1_[1], q1_[2], q1_[3], sg ? z07[2 * kap] : zm9[2 * kap], sg ? z07[2 * kap + 1] : zm9[2 * kap + 1]);
          }
        }
    SPLIT();
#pragma unroll
    for (int i = 0; i < 8; i++) {
      uint32_t h[4];
      ldsm4(h, qa + 128 * i);
      const float ci[4] = {a[i >> 1][0][2 * (i & 1)], a[i >> 1][0][2 * (i & 1) + 1], a[i >> 1][1][2 * (i & 1)], a[i >> 1][1][2 * (i & 1) + 1]};
      mmac(acc[8 + i], h[0], h[1], h[2], h[3], lb0, lb1, ci);
    }
  }
  TS(44);
  {
    uint2 a5[10], a3[10];
    const uint32_t aa = tb + T_5 + 4 * (8 + 2 * g - 2 * c);
#pragma unroll
    for (int m = 0; m < 10; m++) { a5[m] = lds64(aa + 32 * m); a3[m] = lds64(aa + 384 + 32 * m); }
    uint32_t x5[12][2], x3[12][2];
    auto ygen = [&](int kap) {
#pragma unroll
      for (int hh = 0; hh < 2; hh++) {
        float y0, y1, y2, y3;
        mma0(y0, y1, y2, y3, by[0], by[1], by[2], by[3], lds32(y0a + 128 * kap + 64 * hh), lds32(y1a + 128 * kap + 64 * hh));
        x5[kap][hh] = pack_bf(y0, y1);
        x3[kap][hh] = pack_bf(y2, y3);
      }
    };
    ygen(11); ygen(10); ygen(9); ygen(8);
#pragma unroll
    for (int kap = 11; kap >= 0; kap--) {
      if (kap >= 4) ygen(kap - 4);
#pragma unroll
      for (int sg = 0; sg < 2; sg++)
#pragma unroll
        for (int i = 4; i >= 0; i--) {
          const int be = kap + 4 + i;
          if (be <= 15) {
            const uint2 &hi = sg ? a3[2 * i + 1] : a5[2 * i + 1], &lo = sg ? a3[2 * i] : a5[2 * i];
            const uint32_t b0 = sg ? x3[kap][0] : x5[kap][0], b1 = sg ? x3[kap][1] : x5[kap][1];
            if (be < 8 && i == 0 && sg == 0) mma0(acc[be][0], acc[be][1], acc[be][2], acc[be][3], hi.x, hi.y, lo.x, lo.y, b0, b1);
            else mma(acc[be][0], acc[be][1], acc[be][2], acc[be][3], hi.x, hi.y, lo.x, lo.y, b0, b1);
          }
        }
    }
  }
  TS(45);
  {
    const uint32_t st = tb + T_ST + lane * 8;
#pragma unroll
    for (int be = 4; be < 12; be++) sts64(st + 256 * be, pack_bf(acc[be][0], acc[be][1]), pack_bf(acc[be][2], acc[be][3]));
    SPLIT();
    uint32_t F[66], qd[8][4];
    const uint32_t fa = tb + T_D + 32 + 4 * x;
#pragma unroll
    for (int i = 0; i < 32; i++) {
      const int s = 120 - (i >> 2) - 8 * (i & 3);
      uint32_t(&q)[4] = qd[i & 7];
      ldsm4(q, qa + 16 * s);
      const int m = 16 * (i & 3) + 2 * (i >> 2);
      F[m] = lds32(fa + 32 * m); F[m + 1] = lds32(fa + 32 * m + 32);
#pragma unroll
      for (int be = 15; be >= 12; be--) {
        const int de = 8 * be - s;
        float(&a)[4] = (be >= 14 && !(i & 1)) ? acc[be - 4] : acc[be];
        if (de >= 0 && be >= 14 && i == 2 * (15 - be)) mma0(a[0], a[1], a[2], a[3], q[0], q[1], q[2], q[3], F[2 * de + 1], F[2 * de]);
        else if (de >= 0) mma(a[0], a[1], a[2], a[3], q[0], q[1], q[2], q[3], F[2 * de + 1], F[2 * de]);
      }
    }
#pragma unroll
    for (int i = 0; i < 8; i++) acc[14 + (i >> 2)][i & 3] += acc[10 + (i >> 2)][i & 3];
    F[64] = lds32(fa + 32 * 64); F[65] = lds32(fa + 32 * 65);
#pragma unroll
    for (int i = 0; i < 6; i++) ldsm4(qd[i], qa + 128 * 11 - 16 * i);
    uint2 sv = lds64(st + 256 * 11);
    float ci[4] = {bf_lo(sv.x), bf_hi(sv.x), bf_lo(sv.y), bf_hi(sv.y)};
    float T[5][4];
#pragma unroll
    for (int i = 0; i < 16; i++) T[i >> 2][i & 3] = acc[12 + (i >> 2)][i & 3];
    nb_sync(NB_YZ, 160);
    TS(46);
    uint32_t held[2];
#pragma unroll
    for (int be = 11; be >= 0; be--) {
      if (be & 1) SPLITN(be);
      const uint32_t qp = qa + 128 * be;
#pragma unroll
      for (int k = 4; k >= 1; k--) mmac(T[k], qd[0][0], qd[0][1], qd[0][2], qd[0][3], F[16 * k + 1], F[16 * k], T[k - 1]);
      if (be >= 4) mmac(T[0], qd[0][0], qd[0][1], qd[0][2], qd[0][3], F[1], F[0], ci);
      else mma0(T[0][0], T[0][1], T[0][2], T[0][3], qd[0][0], qd[0][1], qd[0][2], qd[0][3], F[1], F[0]);
      ldsm4(qd[6], qp - 16 * 6);
      ldsm4(qd[7], qp - 16 * 7);
      if (be > 4) sv = lds64(st + 256 * (be - 1));
#pragma unroll
      for (int i = 1; i < 8; i++) {
#pragma unroll
        for (int k = 3; k >= 0; k--)
          mma(T[k][0], T[k][1], T[k][2], T[k][3], qd[i][0], qd[i][1], qd[i][2], qd[i][3], F[16 * k + 2 * i + 1], F[16 * k + 2 * i]);
        if (i < 7 && be > 0) ldsm4(qd[i - 1], qp - 128 - 16 * (i - 1));
        if (i == 2) {
          const uint32_t w0 = pack_bf(T[4][0], T[4][1]), w1 = pack_bf(T[4][2], T[4][3]);
          if (be & 1) { held[0] = w0; held[1] = w1; }
          else st_x(ydst + (be + 4) * 16, nz(w0), w1, held[0], held[1]);
          if ((be & 3) == 3 && be < 11) nb_arrive(NB_Y + 2 + (be >> 2), 160);
        }
        if (i == 4 && be > 4) { ci[0] = bf_lo(sv.x); ci[1] = bf_hi(sv.x); ci[2] = bf_lo(sv.y); ci[3] = bf_hi(sv.y); }
      }
    }
    if ((fu(T[0][0]) & fu(T[1][0]) & fu(T[2][0]) & fu(T[3][0])) == 0xffffffffu) sts32(st, 0);
    nb_arrive(NB_BDONE, 288);
    nb_arrive(NB_Y + 1, 160);
#pragma unroll
    for (int B = 1; B >= 0; B--)
      st_x(ydst + B * 32, nz(pack_bf(T[2 * B][0], T[2 * B][1])), pack_bf(T[2 * B][2], T[2 * B][3]),
           pack_bf(T[2 * B + 1][0], T[2 * B + 1][1]), pack_bf(T[2 * B + 1][2], T[2 * B + 1][3]));
  }
}

__device__ __forceinline__ void dual_exp(const uint32_t* w, uint32_t* e) {
  const float L = 1.44268798828125f;
  uint32_t mx = bmax2(bmax2(w[0], w[1]), bmax2(w[2], w[3]));
  uint32_t mn = bmin2(bmin2(w[0], w[1]), bmin2(w[2], w[3]));
  mx = bmax2(mx, __shfl_xor_sync(0xffffffffu, mx, 1));
  mn = bmin2(mn, __shfl_xor_sync(0xffffffffu, mn, 1));
  mx = bmax2(mx, __shfl_xor_sync(0xffffffffu, mx, 2));
  mn = bmin2(mn, __shfl_xor_sync(0xffffffffu, mn, 2));
  const float mx0 = bf_lo(mx) * -L, mx1 = bf_hi(mx) * -L, mn0 = bf_lo(mn) * L, mn1 = bf_hi(mn) * L;
#pragma unroll
  for (int i = 0; i < 2; i++) {
    const float a0 = bf_lo(w[2 * i]), a1 = bf_hi(w[2 * i]), b0 = bf_lo(w[2 * i + 1]), b1 = bf_hi(w[2 * i + 1]);
    e[2 * i] = pack_bf(ex2(fmaf(a0, L, mx0)), ex2(fmaf(b0, L, mx0)));
    e[2 * i + 1] = pack_bf(ex2(fmaf(a1, L, mx1)), ex2(fmaf(b1, L, mx1)));
    e[4 + 2 * i] = pack_bf(ex2(fmaf(a0, -L, mn0)), ex2(fmaf(b0, -L, mn0)));
    e[5 + 2 * i] = pack_bf(ex2(fmaf(a1, -L, mn1)), ex2(fmaf(b1, -L, mn1)));
  }
}
__device__ __forceinline__ void normalise(uint32_t* e, const float (&s)[4]) {
  const uint32_t r = pack_bf(rcp(s[0]), rcp(s[2]));
  const __nv_bfloat162 rr = *(const __nv_bfloat162*)&r;
#pragma unroll
  for (int i = 0; i < 4; i++) {
    const __nv_bfloat162 v = __hmul2(*(const __nv_bfloat162*)&e[i], (i & 1) ? __high2bfloat162(rr) : __low2bfloat162(rr));
    e[i] = *(const uint32_t*)&v;
  }
}
__host__ __device__ constexpr uint64_t qdesc(uint32_t addr) { return mkdesc(addr, 128, 256, 0); }

__global__ void __launch_bounds__(NTHREADS, 1)
fused_kernel(const Params P, const __grid_constant__ CUtensorMap mx, const __grid_constant__ CUtensorMap mw,
             const __grid_constant__ CUtensorMap mo, const __grid_constant__ CUtensorMap mu,
             const __grid_constant__ CUtensorMap mout) {
  constexpr uint32_t sb = SB;
  const int tid = threadIdx.x, lane = tid & 31;
  const int warp = __shfl_sync(0xffffffffu, tid >> 5, 0);
  const int b = blockIdx.x, oct = b >> 3, i8 = b & 7;
  const int rt = (((oct & 4) ? ~oct : oct) & 3) * 2 + (i8 >> 2);
  const int hp = (oct >> 2) * 4 + (i8 & 3);

  const int wg = warp >> 2, w = warp & 3;
  const int d = b * 4 + ((tid >> 5) & 3);
  const KgenRaw raw = kgen_load(P, d, (tid >> 7) & 1, lane, (tid + 128) & 256);
  const uint32_t tb = sb + OFF_T + w * T_CH;
  if (warp >= 12) asm volatile("setmaxnreg.dec.sync.aligned.u32 32;");
  if (warp == 14) {
    asm volatile("prefetch.tensormap [%0];" ::"l"(&mw) : "memory");
    asm volatile("prefetch.tensormap [%0];" ::"l"(&mx) : "memory");
    asm volatile("prefetch.tensormap [%0];" ::"l"(&mu) : "memory");
  }
  if (warp == 12) {
    if (lane == 0) {
#pragma unroll
      for (int i = 0; i < 9; i++) mbar_init(BAR(i), 1);
      asm volatile("fence.mbarrier_init.release.cluster;" ::: "memory");
    }
    __syncwarp();
    if (lane < 9) mbar_expect(BAR(0) + 8 * lane, lane == 0 ? 16384 : 28672);
    __syncwarp();
    nb_arrive(NB_PROD, 384);
#pragma unroll 1
    for (int kb = 0; kb < 8; kb++) {
      if (kb == U_AT) e_tma4d(sb + OFF_STG0, &mu, BAR(MB_URAW), i8 * 64, oct * 2);
      e_tma3d(sb + OFF_W + kb * 12288, &mw, BAR(MB_FULL) + 8 * kb, hp * 32, kb * 64, 0);
      if (kb < 5) e_tma2d(sb + OFF_X + (kb < 2 ? kb + 3 : kb - 2) * 16384, &mx, BAR(MB_FULL) + 8 * kb, kb * 64, rt * 256);
    }
    if (smem_u32(smem_raw) != SB) __trap();
    if (lane == 0) TS1(54);
  }
  if (warp >= 12) {
    if (warp == 12) {
      nb_sync(NB_GATE + 1, 64);
      e_prefetch(P.x + (size_t)(rt * 256 + 128 + hp * 8) * 512, 8192);
      uint32_t slot = sb + OFF_X + 3 * 16384;
#pragma unroll 1
      for (int n = 0; n < 11; n++) {
        mbar_spin(BAR(MB_EMPTY) + 8 * n);
        const int m = n + 5;
        e_tma2d(slot, &mx, BAR(MB_FULL) + 8 * m, (m & 7) * 64, rt * 256 + (m >> 3) * 128);
        slot = slot == sb + OFF_X + 4 * 16384 ? sb + OFF_X : slot + 16384;
        if (n == 7) {
          e_prefetch(P.wo + (size_t)b * 2048, 4096);
          asm volatile("prefetch.tensormap [%0];" ::"l"(&mo) : "memory");
          asm volatile("prefetch.tensormap [%0];" ::"l"(&mout) : "memory");
        }
      }
#pragma unroll 1
      for (int i = 0; i < 8; i++) {
        mbar_wait(BAR(MB_EMPTY + 10) + 8 * ((0x54332222u >> (4 * i)) & 7));
        const int w0 = (0x54736210u >> (4 * i)) & 7;
        e_tma3d(sb + OFF_W + w0 * 16384, &mo, BAR(MB_WO), 0, w0 * 64, (hp & 3) * 2);
      }
    } else {
      if (warp == 13) {
        if (lane == 0) {
#pragma unroll
          for (int i = 9; i < 40; i++) mbar_init(BAR(i), i < MB_EMPTY ? 1 : 4);
          asm volatile("fence.mbarrier_init.release.cluster;" ::: "memory");
        }
        __syncwarp();
        if (lane < 14 && lane != 9) mbar_expect(BAR(MB_FULL + 8) + 8 * lane, lane == 8 ? 131072 : (lane == 10 ? 8192 : (lane == 13 ? 24576 : 16384)));
        nb_arrive(NB_GATE + 1, 64);
      } else if (warp == 14) {
        e_prefetch(P.x + (size_t)(rt * 256 + hp * 8) * 512, 8192);
      }
      nb_sync(NB_PROD, 384);
      if (warp == 15) {
        const uint4 v0 = __ldg((const uint4*)P.wphi + hp * 64 + lane), v1 = __ldg((const uint4*)P.wphi + hp * 64 + 32 + lane);
        sts128(sb + OFF_PHI + (lane & 1) * 256 + (lane >> 1) * 16, v0.x, v0.y, v0.z, v0.w);
        sts128(sb + OFF_PHI + 512 + (lane & 1) * 256 + (lane >> 1) * 16, v1.x, v1.y, v1.z, v1.w);
        const uint32_t one = (((lane >> 3) ^ (lane >> 4)) & 1) ? 0u : ((lane & 1) ? 0x3F800000u : 0x3F80u);
        const int q = (lane >> 1) & 3;
        sts128(sb + OFF_EYE + lane * 16, q == 0 ? one : 0u, q == 1 ? one : 0u, q == 2 ? one : 0u, q == 3 ? one : 0u);
        sts64(sb + OFF_ONE + lane * 8, 0x3F803F80u, 0x3F803F80u);
        asm volatile("fence.proxy.async.shared::cta;" ::: "memory");
        nb_arrive(NB_KREAD, 160);
      }
      uint32_t* cnt = (uint32_t*)(P.xs + X_CNT) + (warp == 13 ? i8 : (warp == 14 ? 8 + rt : 16 + oct)) * 32;
      const unsigned target = (ld_x32(cnt) & ~15u) + 16;
      if (warp != 14) {
        if (warp == 15) mbar_wait(BAR(MB_EMPTY + ZERO_STEP));
        uint4* pz = P.xs + (warp == 13 ? X_PART + (hp * 8 + rt) * 144 : X_Y + b * 1024) + lane;
#pragma unroll 1
        for (int i = (warp == 13 ? 144 : 1024) - lane; i > 0; i -= 32, pz += 32) st_x(pz, 0, 0, 0, 0);
      }
      if (warp == 15) __syncwarp();
      else nb_sync(warp == 13 ? NB_INIT : NB_ODONE, warp == 13 ? 160 : 288);
      if (lane == 0) asm volatile("red.release.gpu.global.add.u32 [%0], %1;" ::"l"(cnt), "r"(warp == 15 ? 2 : 1) : "memory");
      if (lane == 0) TS1(warp == 13 ? 50 : (warp == 14 ? 57 : 53));
      __syncwarp();
      if (warp == 14) nb_arrive(NB_GATE + 1, 160);
      asm volatile("fence.proxy.async.shared::cta;" ::: "memory");
      if (warp == 13) cnt += ((lane & 1 ? b >> 4 : i8 ^ (lane & 4)) - i8) * 32;
#pragma unroll 1
      for (int i = 0; i < SPIN_MAX; i++) {
        unsigned v;
        asm volatile("ld.acquire.gpu.global.u32 %0, [%1];" : "=r"(v) : "l"(cnt) : "memory");
        if (__all_sync(0xffffffffu, (int)(v - target) >= 0)) break;
      }
      if (lane == 0) TS1(warp == 13 ? 51 : (warp == 14 ? 58 : 55));
      if (warp == 15) { nb_arrive(NB_YZ, 160); return; }
      asm volatile("fence.proxy.async.global;" ::: "memory");
      if (warp == 13) {
        mbar_wait(BAR(MB_EMPTY + 11));
        e_expect(BAR(MB_UFULL), 4 * U_CH);
        e_bulk(sb + OFF_U, P.xs + X_UT + b * (U_CH / 4), 4 * U_CH, BAR(MB_UFULL));
      } else {
        const uint4* src = P.xs + X_O + (rt * 4 + (hp >> 2)) * 4096;
        e_bulk(sb + OFF_X + 32768 + 57344, src + 3584, 8192, BAR(MB_O));
        e_bulk(sb + OFF_X + 32768, src, 16384, BAR(MB_O + 1));
        e_bulk(sb + OFF_X + 49152, src + 1024, 16384, BAR(MB_O + 2));
        e_bulk(sb + OFF_STG0, src + 3200, 6144, BAR(MB_O + 3));
        nb_sync(NB_BDONE, 288);
        asm volatile("fence.proxy.async.shared::cta;" ::: "memory");
        e_bulk(sb + OFF_U, src + 2048, 18432, BAR(MB_O + 3));
      }
    }
    return;
  }

  asm volatile("setmaxnreg.inc.sync.aligned.u32 160;");
  const int t = tid & 127;
  const int g = lane >> 2, c = lane & 3;
  const uint32_t kp = ((tb + 127) & ~127u) + (wg & 1) * 2048;
  const KgenAddr kad = kgen_addr(lane, kp);
  if (wg) nb_sync(NB_PROD, 384);
  SPLIT();
  float k[5][4], k2048, ksc;
  if (wg) {
    kgen_unit(raw, kad, blockIdx.y, k, k2048, ksc);
    TS(40 + wg);
    if ((fu(k[0][0]) & fu(k[1][0]) & fu(k[2][0]) & fu(k[3][0]) & fu(k[4][0])) == 0xffffffffu) sts32(kp, 0);
  }
  if (wg) nb_arrive(0, 384);
  if (wg) {
    if (wg == 1) {
      uint32_t h[10];
#pragma unroll
      for (int j = 0; j < 10; j++) h[j] = hu(__floats2half2_rn(k[j >> 1][2 * (j & 1)], k[j >> 1][2 * (j & 1) + 1]));
      sts128(kp + lane * 16, h[0], h[1], h[2], h[3]);
      sts128(kp + 512 + lane * 16, h[4], h[5], h[6], h[7]);
      sts128(kp + 1024 + lane * 16, h[8], h[9], fu(k2048), fu(ksc));
      nb_arrive(NB_PREP, 256);
    }
  } else {
    nb_sync(NB_KREAD, 160);
  }
  if (wg == 1) {
    mbar_wait(BAR(MB_URAW));
    TS(48);
    uint4* dst = P.xs + X_UT + (i8 * 64 + g) * (U_CH / 16) + (w & 1) * (U_ODD / 16) + U_PAD / 16 + oct * 8 + (w >> 1) * 4 + c;
    const int ln = ((lane >> 1) & 3) + 4 * (lane & 1);
    uint32_t r[8][4];
#pragma unroll
    for (int i = 0; i < 8; i++) ldsm4t(r[i], sb + OFF_STG0 + w * 4096 + ((lane >> 3) * 8 + ln) * 128 + ((i ^ ln) << 4));
#pragma unroll
    for (int i = 0; i < 8; i++) dst[i * (U_CH / 2)] = make_uint4(r[i][0], r[i][1], r[i][2], r[i][3]);
    nb_arrive(NB_INIT, 160);
    if (lane == 0) mbar_arrive(BAR(MB_AUX));
  }
  {
    if (wg == 2) {
#pragma unroll
      for (int j = 0; j < 5; j++) { k[j][0] *= ksc; k[j][1] *= ksc; k[j][2] *= ksc; k[j][3] *= ksc; }
      const unsigned short dsk = __ldg((const unsigned short*)P.Dskip + d);
      nb_sync(NB_PREP, 256);
      {
        const uint32_t src = kp + 2048 + lane * 16;
        const uint4 v0 = lds128(src), v1 = lds128(src + 512), v2 = lds128(src + 1024);
        const uint32_t h[10] = {v0.x, v0.y, v0.z, v0.w, v1.x, v1.y, v1.z, v1.w, v2.x, v2.y};
#pragma unroll
        for (int j = 0; j < 10; j++) {
          const float2 f = __half22float2(*(const __half2*)&h[j]);
          k[j >> 1][2 * (j & 1)] = fmaf(f.x, uf(v2.w), k[j >> 1][2 * (j & 1)]);
          k[j >> 1][2 * (j & 1) + 1] = fmaf(f.y, uf(v2.w), k[j >> 1][2 * (j & 1) + 1]);
        }
        k2048 += uf(v2.z);
      }
#pragma unroll
      for (int o2 = 16; o2; o2 >>= 1) k2048 += __shfl_xor_sync(0xffffffffu, k2048, o2);
      if (lane == 0) k[0][0] += bf_lo(dsk);
      __syncwarp();
      TS(34);
      build_tables(tb, lane, k, k2048);
      TS(35);
      uint4* const g_y = P.xs + X_Y;
      conv_channel(sb + OFF_U + w * U_CH, tb, lane, g_y + (size_t)d * 256 + lane);
      nb_arrive(NB_Y, 160);
      TS(37);
      if (w == 0) TSDUMP(32);
      return;
    }
    if (wg == 1) {
      mbar_wait(BAR(MB_EMPTY + 4));
      mbar_spin(BAR(MB_EMPTY + 6));
    }
    TS(wg * 16 + 1);
  }

  float acc[2][48];
  {
    uint32_t fb = BAR(MB_FULL) + 64 * wg;
    uint32_t da = (uint32_t)mkdesc(sb + OFF_X, 16, 0, 0) + (wg ? 1024 : 3072), db = (uint32_t)mkdesc(sb + OFF_W, 4096, 0, 0);
    constexpr uint64_t ha = mkdesc(0, 0, 1024, 1), hb = mkdesc(0, 0, 512, 2);
    mbar_spin(fb);
    if (wg == 0) nb_sync(0, 384);
    TS(wg * 16 + 2);
#pragma unroll 1
    for (int kb = 0; kb < 8; kb++) {
      WG_FENCE();
#pragma unroll
      for (int k = 0; k < 4; k++) {
        wgmma_ss_n96(acc[0], ha | (da + 2 * k), hb | (db + 64 * k), k ? 1 : kb);
        wgmma_ss_n96(acc[1], ha | (da + 2 * k + 512), hb | (db + 64 * k), k ? 1 : kb);
      }
      WG_COMMIT();
      if (kb < 7) mbar_spin(fb + 8);
      WG_WAIT(1);
      if (kb > 0) e_arrive(fb + 8 * (MB_EMPTY - MB_FULL - 1));
      fb += 8; db += 768;
      da = da == (uint32_t)mkdesc(sb + OFF_X + 65536, 16, 0, 0) ? da - 4096 : da + 1024;
    }
    WG_WAIT(0);
    e_arrive(fb + 8 * (MB_EMPTY - MB_FULL - 1));
    SPLIT();
  }
  TS(wg * 16 + 3);

  constexpr uint32_t stg0 = sb + OFF_STG0, stg1 = sb + OFF_X + 32768;
  uint4* const g_part = P.xs + X_PART;
  uint4* const g_o = P.xs + X_O;
  constexpr uint32_t kvs = stg0;
  auto pack8 = [](const float* a) { return make_uint4(pack_bf(a[0], a[1]), pack_bf(a[2], a[3]), pack_bf(a[4], a[5]), pack_bf(a[6], a[7])); };
  auto stage_k = [&](auto nt, const uint4* af, const uint4* vp, uint32_t sl, uint32_t free_bar) {
    constexpr int NU = 2 * decltype(nt)::value;
    float p[NU][8], rs[2 * NU][4];
    uint32_t ek[8 * NU];
    WG_FENCE();
#pragma unroll
    for (int u = 0; u < NU; u++) wgmma_rs_n16(p[u], af[u], qdesc(sb + OFF_PHI + (u & 1) * 512), 0);
    WG_COMMIT();
    WG_WAIT(0);
#pragma unroll
    for (int u = 0; u < NU; u++) {
      const uint32_t pw[4] = {pack_bf(p[u][0], p[u][2]), pack_bf(p[u][1], p[u][3]), pack_bf(p[u][4], p[u][6]), pack_bf(p[u][5], p[u][7])};
      dual_exp(pw, ek + 8 * u);
    }
    TS(wg * 16 + 12);
    mbar_spin(free_bar);
    WG_FENCE();
#pragma unroll
    for (int i = 0; i < 2 * NU; i++) wgmma_rs_n8(rs[i], make_uint4(ek[4 * i], ek[4 * i + 1], ek[4 * i + 2], ek[4 * i + 3]), qdesc(sb + OFF_ONE), 0);
    WG_COMMIT();
#pragma unroll
    for (int i = 0; i < NU; i++) stsm4(sl + (i >> 1) * 4 * SLAB + 2048 + (i & 1) * 512, vp[i].x, vp[i].y, vp[i].z, vp[i].w);
    if (NU == 4 || lane < 16) sts128(sl + (lane >> 4) * (4 * SLAB - 256) + 3072, 0x3F803F80u, 0x3F803F80u, 0x3F803F80u, 0x3F803F80u);
    WG_WAIT(0);
#pragma unroll
    for (int i = 0; i < 2 * NU; i++) {
      normalise(ek + 4 * i, rs[i]);
      stsm4(sl + (i >> 2) * 4 * SLAB + (i & 3) * 512, ek[4 * i], ek[4 * i + 1], ek[4 * i + 2], ek[4 * i + 3]);
    }
    asm volatile("fence.proxy.async.shared::cta;" ::: "memory");
  };
  auto contract = [&](float (&kc)[20], uint32_t stg, int acc_in) {
    WG_FENCE();
#pragma unroll
    for (int s = 0; s < 8; s++) wgmma_ss_n40(kc, qdesc(stg + s * SLAB), qdesc(stg + s * SLAB + 2048), s ? 1 : acc_in);
    WG_COMMIT();
    WG_WAIT(0);
  };
  uint32_t eq[32];
  {
    uint4 af[4], aq[4], vp[4];
    float kc[20];
#pragma unroll
    for (int u = 0; u < 4; u++) { af[u] = pack8(acc[u >> 1] + 16 + 8 * (u & 1)); vp[u] = pack8(acc[u >> 1] + 32 + 8 * (u & 1)); }
    const uint32_t hand = stg1 + 16384 + 8192 + w * 2048 + lane * 16;
    if (wg) {
      sts128(hand, af[2].x, af[2].y, af[2].z, af[2].w); sts128(hand + 512, af[3].x, af[3].y, af[3].z, af[3].w);
      sts128(hand + 1024, vp[2].x, vp[2].y, vp[2].z, vp[2].w); sts128(hand + 1536, vp[3].x, vp[3].y, vp[3].z, vp[3].w);
      nb_arrive(NB_HAND, 256);
    }
#pragma unroll
    for (int u = 0; u < 4; u++) aq[u] = pack8(acc[u >> 1] + 8 * (u & 1));
    if (wg == 0) {
      stage_k(std::integral_constant<int, 2>(), af, vp, stg0 + w * SLAB + lane * 16, BAR(MB_AUX));
      TS(13);
      nb_sync(NB_WG0, 128);
      contract(kc, stg0, 0);
      mbar_wait(BAR(MB_UFULL));
      TS(15);
      nb_sync(NB_HAND, 256);
      af[0] = lds128(hand); af[1] = lds128(hand + 512); vp[0] = lds128(hand + 1024); vp[1] = lds128(hand + 1536);
      nb_sync(NB_WG0, 128);
    }
    stage_k(std::integral_constant<int, 1>(), af, vp, stg1 + (wg ? w : 4 + w) * SLAB + lane * 16, BAR(MB_EMPTY + 15));
    TS(wg * 16 + 14);
    float p[4][8];
    if (wg) {
      nb_arrive(NB_ST0, 256);
      nb_arrive(NB_GATE, 256);
    } else {
      uint4* pp = g_part + (size_t)(hp * 8 + rt) * 144 + t;
      uint32_t* pz = (uint32_t*)(pp - t + 128) + w * 16 + c * 8 + g;
      asm volatile("" : "+l"(pp), "+l"(pz));
      nb_sync(NB_ST0, 256);
      contract(kc, stg1, 1);
      TS(6);
      float kv[8];
#pragma unroll
      for (int i = 0; i < 8; i++) kv[i] = w & 2 ? kc[8 + i] : kc[i];
      st_x(pp, nz(pack_bf(kv[0], kv[1])), pack_bf(kv[2], kv[3]), pack_bf(kv[4], kv[5]), pack_bf(kv[6], kv[7]));
      if (c < 2) st_x32(pz, nz(fu(c ? kc[18] : kc[16])));
      TS(5);
    }
    SPLIT();
    WG_FENCE();
#pragma unroll
    for (int u = 0; u < 4; u++) wgmma_rs_n16(p[u], aq[u], qdesc(sb + OFF_PHI + (u & 1) * 512), 0);
    WG_COMMIT();
    WG_WAIT(0);
#pragma unroll
    for (int u = 0; u < 4; u++) {
      const uint32_t pw[4] = {pack_bf(p[u][0], p[u][2]), pack_bf(p[u][1], p[u][3]), pack_bf(p[u][4], p[u][6]), pack_bf(p[u][5], p[u][7])};
      dual_exp(pw, eq + 8 * u);
    }
    SPLIT();
  }
  TS(wg * 16 + 4);
  if (wg == 1) {
    mbar_wait(BAR(MB_UFULL));
    const uint4* ps = g_part + (size_t)hp * 8 * 144 + t;
    const uint32_t* zs = (const uint32_t*)(g_part + (size_t)(hp * 8 + (lane >> 4) * 4) * 144 + 128) + w * 16 + (lane & 15);
    uint4 v[8];
    uint32_t zv[4];
#pragma unroll 1
    for (int it = 0; it < SPIN_MAX; it++) {
#pragma unroll
      for (int i = 0; i < 8; i++) v[i] = ld_x(ps + i * 144);
#pragma unroll
      for (int i = 0; i < 4; i++) zv[i] = ld_x32(zs + i * 576);
      uint32_t m = min(min(zv[0], zv[1]), min(zv[2], zv[3]));
#pragma unroll
      for (int i = 0; i < 8; i++) m = min(m, v[i].x);
      if (__all_sync(0xffffffffu, m != 0)) break;
    }
    float s[8];
    WG_FENCE();
#pragma unroll
    for (int r = 0; r < 8; r++) wgmma_rs_n16(s, v[r], qdesc(sb + OFF_EYE), r);
    WG_COMMIT();
    float zsum = (uf(zv[0]) + uf(zv[1])) + (uf(zv[2]) + uf(zv[3]));
    zsum += __shfl_xor_sync(0xffffffffu, zsum, 16);
    const uint32_t z1 = pack_bf(zsum, 1.f);
    if (lane < 16) sts128(kvs + w * 768 + 512 + lane * 16, z1, z1, z1, z1);
    WG_WAIT(0);
    stsm4(kvs + w * 768 + lane * 16, pack_bf(s[0], s[1]), pack_bf(s[2], s[3]), pack_bf(s[4], s[5]), pack_bf(s[6], s[7]));
    asm volatile("fence.proxy.async.shared::cta;" ::: "memory");
    TS(22);
  }
  nb_sync(NB_KV, 256);
  {
    float n[8][12];
    WG_FENCE();
#pragma unroll
    for (int i = 0; i < 8; i++) wgmma_rs_n24(n[i], make_uint4(eq[4 * i], eq[4 * i + 1], eq[4 * i + 2], eq[4 * i + 3]), qdesc(kvs + (i & 3) * 768), 0);
    WG_COMMIT();
    uint32_t* od = (uint32_t*)(g_o + (size_t)((rt * 4 + wg * 2) * 32 + hp * 2) * 128) + w * 64 + lane;
    WG_WAIT(0);
#pragma unroll
    for (int u = 0; u < 4; u++) {
      float(&np)[12] = n[2 * u];
      const float(&nm)[12] = n[2 * u + 1];
      const float q0 = np[9] * rcp(nm[9]), q1 = np[11] * rcp(nm[11]);
      const float r0 = rcp(fmaf(nm[8], q0, fmaf(np[9], 1e-6f, np[8]))), r1 = rcp(fmaf(nm[10], q1, fmaf(np[11], 1e-6f, np[10])));
#pragma unroll
      for (int i = 0; i < 8; i++) np[i] = fmaf(nm[i], (i & 2) ? q1 : q0, np[i]);
      uint32_t* o = od + (u >> 1) * 16384 + (u & 1) * 512;
      o[0] = pack_bf(np[0] * r0, np[1] * r0);
      o[32] = pack_bf(np[2] * r1, np[3] * r1);
      o[256] = pack_bf(np[4] * r0, np[5] * r0);
      o[288] = pack_bf(np[6] * r1, np[7] * r1);
      if (u == 1) SPLIT();
    }
  }
  TS(wg * 16 + 7);
  nb_arrive(NB_ODONE, 288);
  if (wg) {
    const uint4* src = P.xs + X_Y + (oct * 32 + c * 8) * 256 + (2 * w + (g >> 2)) * 32 + i8 * 4 + (g & 3);
    __nv_bfloat16* dst = P.out + (size_t)((2 * w + (g >> 2)) * 256 + i8 * 16 + (g & 3) * 2) * 1024 + 512 + oct * 32 + c * 8;
    nb_sync(NB_GATE + 1, 160);
    nb_sync(NB_Y + w, 160);
    uint4 v[8];
#pragma unroll 1
    for (int it = 0; it < SPIN_MAX; it++) {
      uint32_t m = 0xffffffffu;
#pragma unroll
      for (int i = 0; i < 8; i++) v[i] = ld_x(src + i * 256);
#pragma unroll
      for (int i = 0; i < 8; i++) m = min(m, v[i].x);
      if (__all_sync(0xffffffffu, m != 0)) break;
    }
#pragma unroll
    for (int i = 0; i < 8; i++) *(uint4*)(dst + (size_t)((i >> 2) * 128 + ((i >> 1) & 1) * 8 + (i & 1)) * 1024) = tr_row(v, i);
    TS(31);
    GT(63);
    if (w == 0) TSDUMP(16);
    return;
  }
  mbar_wait(BAR(MB_WO));
  nb_sync(NB_BDONE, 288);
  TS(8);
  mbar_spin(BAR(MB_O));
  TS(9);
  constexpr uint64_t ha = mkdesc(0, 0, 128, 0), hb = mkdesc(0, 0, 1024, 1);
  constexpr uint32_t da0 = (uint32_t)mkdesc(stg1, 1024, 0, 0), db0 = (uint32_t)mkdesc(sb + OFF_W, 8192, 0, 0);
  const uint32_t ot = ((sb + OFF_T + 1023) & ~1023u) + w * 4096;
  auto store_half = [&](const float* oc, int hf) {
#pragma unroll
    for (int i = 0; i < 8; i += 2)
      stsm4(ot + hf * 2048 + (lane & 15) * 128 + (((i + (lane >> 4)) ^ lane) & 7) * 16, pack_bf(oc[4 * i], oc[4 * i + 1]),
            pack_bf(oc[4 * i + 2], oc[4 * i + 3]), pack_bf(oc[4 * i + 4], oc[4 * i + 5]), pack_bf(oc[4 * i + 6], oc[4 * i + 7]));
    asm volatile("fence.proxy.async.shared::cta;" ::: "memory");
    __syncwarp();
    e_store2d(&mout, ot + hf * 2048, (hp & 3) * 128 + hf * 64, (rt * 4 + (hp >> 2)) * 64 + w * 16);
  };
  float oc[64];
#pragma unroll 1
  for (int j = 0; j < 8; j++) {
    const int kb = (j + 7) & 7;
    if ((j & 1) && j < 6) mbar_spin(BAR(MB_O + 1) + 4 * (j - 1));
    WG_FENCE();
#pragma unroll
    for (int k = 0; k < 4; k++) wgmma_ss_n128(oc, ha | (da0 + 512 * kb + 128 * k), hb | (db0 + 1024 * kb + 128 * k), k ? 1 : j);
    WG_COMMIT();
  }
  WG_WAIT(0);
  TS(10);
  store_half(oc, 0);
  store_half(oc + 32, 1);
  asm volatile(ELECT "cp.async.bulk.commit_group;\n@p cp.async.bulk.wait_group.read 0;\n}\n" ::: "memory");
  TS(wg * 16 + 11);
  GT(61 + wg);
  if (w == 0) TSDUMP(0);
  if (w == 1) TSDUMP(48);
}

typedef CUresult (*EncodeFn)(CUtensorMap*, CUtensorMapDataType, cuuint32_t, void*, const cuuint64_t*, const cuuint64_t*,
                             const cuuint32_t*, const cuuint32_t*, CUtensorMapInterleave, CUtensorMapSwizzle,
                             CUtensorMapL2promotion, CUtensorMapFloatOOBfill);

}

extern "C" void kernel_launch(void* const* d_in, const int* in_sizes, int n_in, void* d_out, int out_size) {
  (void)in_sizes; (void)n_in; (void)out_size;
  void* fn = nullptr;
  cudaDriverEntryPointQueryResult qr;
  cudaGetDriverEntryPoint("cuTensorMapEncodeTiled", &fn, cudaEnableDefault, &qr);
  EncodeFn enc = (EncodeFn)fn;
  CUtensorMap mx, mw, mo, mu, mout;
  const cuuint32_t es[5] = {1, 1, 1, 1, 1};
  {
    cuuint64_t dims[2] = {512, 2048}, st[1] = {1024};
    cuuint32_t box[2] = {64, 128};
    enc(&mx, CU_TENSOR_MAP_DATA_TYPE_BFLOAT16, 2, d_in[0], dims, st, box, es, CU_TENSOR_MAP_INTERLEAVE_NONE,
        CU_TENSOR_MAP_SWIZZLE_128B, CU_TENSOR_MAP_L2_PROMOTION_L2_128B, CU_TENSOR_MAP_FLOAT_OOB_FILL_NONE);
  }
  {
    cuuint64_t dims[3] = {512, 512, 3}, st[2] = {3072, 1024};
    cuuint32_t box[3] = {32, 64, 3};
    enc(&mw, CU_TENSOR_MAP_DATA_TYPE_BFLOAT16, 3, d_in[1], dims, st, box, es, CU_TENSOR_MAP_INTERLEAVE_NONE,
        CU_TENSOR_MAP_SWIZZLE_64B, CU_TENSOR_MAP_L2_PROMOTION_L2_128B, CU_TENSOR_MAP_FLOAT_OOB_FILL_NONE);
  }
  {
    cuuint64_t dims[3] = {64, 512, 8}, st[2] = {1024, 128};
    cuuint32_t box[3] = {64, 64, 2};
    enc(&mo, CU_TENSOR_MAP_DATA_TYPE_BFLOAT16, 3, d_in[3], dims, st, box, es, CU_TENSOR_MAP_INTERLEAVE_NONE,
        CU_TENSOR_MAP_SWIZZLE_128B, CU_TENSOR_MAP_L2_PROMOTION_L2_128B, CU_TENSOR_MAP_FLOAT_OOB_FILL_NONE);
  }
  {
    cuuint64_t dims[4] = {512, 4, 16, 32}, st[3] = {16384, 1024, 65536};
    cuuint32_t box[4] = {64, 4, 16, 2};
    enc(&mu, CU_TENSOR_MAP_DATA_TYPE_BFLOAT16, 4, d_in[4], dims, st, box, es, CU_TENSOR_MAP_INTERLEAVE_NONE,
        CU_TENSOR_MAP_SWIZZLE_128B, CU_TENSOR_MAP_L2_PROMOTION_L2_128B, CU_TENSOR_MAP_FLOAT_OOB_FILL_NONE);
  }
  {
    cuuint64_t dims[2] = {1024, 2048}, st[1] = {2048};
    cuuint32_t box[2] = {64, 16};
    enc(&mout, CU_TENSOR_MAP_DATA_TYPE_BFLOAT16, 2, d_out, dims, st, box, es, CU_TENSOR_MAP_INTERLEAVE_NONE,
        CU_TENSOR_MAP_SWIZZLE_128B, CU_TENSOR_MAP_L2_PROMOTION_NONE, CU_TENSOR_MAP_FLOAT_OOB_FILL_NONE);
  }
  Params P;
  P.x = (const __nv_bfloat16*)d_in[0];
  P.wphi = (const __nv_bfloat16*)d_in[2];
  P.wo = (const __nv_bfloat16*)d_in[3];
  P.logA = (const __nv_bfloat16*)d_in[5];
  P.Aim = (const __nv_bfloat16*)d_in[6];
  P.Cre = (const __nv_bfloat16*)d_in[7];
  P.Cim = (const __nv_bfloat16*)d_in[8];
  P.logdt = (const __nv_bfloat16*)d_in[9];
  P.Dskip = (const __nv_bfloat16*)d_in[10];
  P.out = (__nv_bfloat16*)d_out;
  cudaGetSymbolAddress((void**)&P.xs, g_x);
  P.ts = nullptr;
  cudaFuncSetAttribute(fused_kernel, cudaFuncAttributeMaxDynamicSharedMemorySize, SMEM_BYTES);
  fused_kernel<<<NCTA, NTHREADS, SMEM_BYTES>>>(P, mx, mw, mo, mu, mout);
}
```

```cpp
#include <cuda_runtime.h>
#include <cuda_bf16.h>
#include <cuda_fp16.h>
#include <cuda.h>
#include <stdint.h>
#include <type_traits>

#define DBG_TS 0

namespace {

constexpr int NTHREADS = 512;
constexpr int NCTA = 128;
constexpr int OFF_W = 0;
constexpr int OFF_X = 98304;
constexpr int OFF_U = OFF_X + 65536;
constexpr int U_CH = 4416, U_ODD = 2240, U_PAD = 128;
constexpr int OFF_STG0 = OFF_U + 18432;
constexpr int SLAB = 3328;
constexpr int OFF_T = OFF_STG0 + 8 * SLAB;
constexpr int T_CH = 5216;
constexpr int T_D = 0;
constexpr int T_5 = 2144;
constexpr int T_3 = T_5 + 384;
constexpr int T_7 = T_5 + 1024;
constexpr int T_9 = T_7 + 320;
constexpr int T_KC = T_9 + 320;
constexpr int T_ST = T_5 - 1024;
constexpr int OFF_PHI = OFF_T + 4 * T_CH;
constexpr int OFF_EYE = OFF_PHI + 1024, OFF_ONE = OFF_EYE + 512;
constexpr int OFF_BAR = OFF_ONE + 256;
constexpr int SMEM_BYTES = OFF_BAR + 512 + 256 * DBG_TS;
constexpr uint32_t SB = 1024;
static_assert(T_KC + 2 * 656 <= T_CH, "table size");
static_assert(SMEM_BYTES <= 232448, "smem");
constexpr int MB_URAW = 0, MB_FULL = 1  , MB_WO = 17, MB_UFULL = 18, MB_O = 19  ,
              MB_EMPTY = 23  , MB_AUX = 39;
__host__ __device__ constexpr uint32_t BAR(int i) { return SB + OFF_BAR + 8 * i; }
constexpr int NB_WG0 = 1, NB_ODONE = 2, NB_ST0 = 3, NB_HAND = 4, NB_KV = 5, NB_YZ = 6, NB_INIT = 7, NB_PREP = 8, NB_PROD = 9, NB_KREAD = 10,
              NB_BDONE = 11, NB_GATE = 12  , NB_Y = 7  ;
constexpr int U_AT = 2;
constexpr int ZERO_STEP = 12;
constexpr int SPIN_MAX = 1 << 16;

constexpr int X_CNT = 0;
constexpr int X_PART = 256;
constexpr int X_O = X_PART + 16 * 8 * 144;
constexpr int X_Y = X_O + 32 * 32 * 128;
constexpr int X_UT = X_Y + 512 * 8 * 32;
constexpr int X_SIZE = X_UT + 512 * (U_CH / 16);
__device__ __align__(128) uint4 g_x[X_SIZE];
extern __shared__ uint8_t smem_raw[];
#define TS(i) do {} while (0)
#define TS1(i) do {} while (0)
#define GT(i) do {} while (0)
#define TSDUMP(base) do {} while (0)

__device__ __forceinline__ uint32_t smem_u32(const void* p) { return (uint32_t)__cvta_generic_to_shared(p); }
__device__ __forceinline__ void mbar_arrive(uint32_t b) {
  asm volatile("mbarrier.arrive.shared::cta.b64 _, [%0];" ::"r"(b) : "memory");
}
__device__ __forceinline__ void mbar_wait(uint32_t b) {
  uint32_t done = 0;
#pragma unroll 1
  for (int i = 0; i < SPIN_MAX && !done; i++) {
    asm volatile("{\n.reg .pred p;\nmbarrier.try_wait.parity.shared::cta.b64 p, [%1], 0, 4000;\nselp.u32 %0, 1, 0, p;\n}\n"
                 : "=r"(done) : "r"(b) : "memory");
  }
}
__device__ __forceinline__ void mbar_spin(uint32_t b) {
  uint32_t done = 0;
#pragma unroll 1
  for (int i = 0; i < (SPIN_MAX << 4) && !done; i++) {
    asm volatile("{\n.reg .pred p;\nmbarrier.try_wait.parity.shared::cta.b64 p, [%1], 0;\nselp.u32 %0, 1, 0, p;\n}\n"
                 : "=r"(done) : "r"(b) : "memory");
  }
}
__device__ __forceinline__ uint32_t mbar_test(uint32_t b) {
  uint32_t done;
  asm volatile("{\n.reg .pred p;\nmbarrier.test_wait.parity.shared::cta.b64 p, [%1], 0;\nselp.u32 %0, 1, 0, p;\n}\n" : "=r"(done) : "r"(b) : "memory");
  return done;
}
__device__ __forceinline__ void mbar_init(uint32_t b, int n) {
  asm volatile("mbarrier.init.shared::cta.b64 [%0], %1;" ::"r"(b), "r"(n) : "memory");
}
__device__ __forceinline__ void mbar_expect(uint32_t b, int bytes) {
  asm volatile("mbarrier.arrive.expect_tx.shared::cta.b64 _, [%0], %1;" ::"r"(b), "r"(bytes) : "memory");
}
__device__ __forceinline__ void nb_sync(int id, int n) { asm volatile("bar.sync %0, %1;" ::"r"(id), "r"(n) : "memory"); }
__device__ __forceinline__ void nb_arrive(int id, int n) { asm volatile("bar.arrive %0, %1;" ::"r"(id), "r"(n) : "memory"); }
#define ELECT "{\n.reg .pred p;\nelect.sync _|p, 0xffffffff;\n@p "
__device__ __forceinline__ void e_arrive(uint32_t b) {
  asm volatile(ELECT "mbarrier.arrive.shared::cta.b64 _, [%0];\n}\n" ::"r"(b) : "memory");
}
__device__ __forceinline__ void e_expect(uint32_t b, int bytes) {
  asm volatile(ELECT "mbarrier.arrive.expect_tx.shared::cta.b64 _, [%0], %1;\n}\n" ::"r"(b), "r"(bytes) : "memory");
}
__device__ __forceinline__ void e_tma2d(uint32_t dst, const CUtensorMap* m, uint32_t bar, int c0, int c1) {
  asm volatile(ELECT "cp.async.bulk.tensor.2d.shared::cluster.global.mbarrier::complete_tx::bytes [%0], [%1, {%3,%4}], [%2];\n}\n"
               ::"r"(dst), "l"(m), "r"(bar), "r"(c0), "r"(c1) : "memory");
}
__device__ __forceinline__ void e_tma3d(uint32_t dst, const CUtensorMap* m, uint32_t bar, int c0, int c1, int c2) {
  asm volatile(ELECT "cp.async.bulk.tensor.3d.shared::cluster.global.mbarrier::complete_tx::bytes [%0], [%1, {%3,%4,%5}], [%2];\n}\n"
               ::"r"(dst), "l"(m), "r"(bar), "r"(c0), "r"(c1), "r"(c2) : "memory");
}
__device__ __forceinline__ void e_tma4d(uint32_t dst, const CUtensorMap* m, uint32_t bar, int c0, int c3) {
  asm volatile(ELECT "cp.async.bulk.tensor.4d.shared::cluster.global.mbarrier::complete_tx::bytes [%0], [%1, {%3,%5,%5,%4}], [%2];\n}\n"
               ::"r"(dst), "l"(m), "r"(bar), "r"(c0), "r"(c3), "r"(0) : "memory");
}
__device__ __forceinline__ void e_bulk(uint32_t dst, const void* src, int bytes, uint32_t bar) {
  asm volatile(ELECT "cp.async.bulk.shared::cluster.global.mbarrier::complete_tx::bytes [%0], [%1], %2, [%3];\n}\n"
               ::"r"(dst), "l"(src), "r"(bytes), "r"(bar) : "memory");
}
__device__ __forceinline__ void e_prefetch(const void* p, int bytes) {
  asm volatile(ELECT "cp.async.bulk.prefetch.L2.global [%0], %1;\n}\n" ::"l"(p), "r"(bytes) : "memory");
}
__device__ __forceinline__ void e_store2d(const CUtensorMap* m, uint32_t src, int c0, int c1) {
  asm volatile(ELECT "cp.async.bulk.tensor.2d.global.shared::cta.bulk_group [%0, {%2,%3}], [%1];\n}\n"
               ::"l"(m), "r"(src), "r"(c0), "r"(c1) : "memory");
}
__host__ __device__ constexpr uint64_t mkdesc(uint32_t addr, uint32_t lbo, uint32_t sbo, int swz) {
  return (uint64_t)((addr & 0x3FFFF) >> 4) | ((uint64_t)(lbo >> 4) << 16) | ((uint64_t)(sbo >> 4) << 32) |
         ((uint64_t)swz << 62);
}
#define SPLIT() asm volatile("{\n.reg .pred p;\nsetp.eq.u32 p, %0, %1;\n@p exit;\n}\n" ::"r"(blockIdx.y), "n"(__LINE__) : "memory")
#define SPLITN(n) asm volatile("{\n.reg .pred p;\nsetp.eq.u32 p, %0, %1;\n@p exit;\n}\n" ::"r"(blockIdx.y), "r"(4096 + (n)) : "memory")
#define WG_FENCE() asm volatile("wgmma.fence.sync.aligned;" ::: "memory")
#define WG_COMMIT() asm volatile("wgmma.commit_group.sync.aligned;" ::: "memory")
#define WG_WAIT(n) asm volatile("wgmma.wait_group.sync.aligned " #n ";" ::: "memory")

__device__ __forceinline__ void mma(float& d0, float& d1, float& d2, float& d3, uint32_t a0, uint32_t a1, uint32_t a2,
                                    uint32_t a3, uint32_t b0, uint32_t b1) {
  asm volatile("mma.sync.aligned.m16n8k16.row.col.f32.bf16.bf16.f32 {%0,%1,%2,%3},{%4,%5,%6,%7},{%8,%9},{%0,%1,%2,%3};"
               : "+f"(d0), "+f"(d1), "+f"(d2), "+f"(d3)
               : "r"(a0), "r"(a1), "r"(a2), "r"(a3), "r"(b0), "r"(b1));
}
__device__ __forceinline__ void mmac(float (&d)[4], uint32_t a0, uint32_t a1, uint32_t a2, uint32_t a3, uint32_t b0,
                                     uint32_t b1, const float (&c)[4]) {
  asm volatile("mma.sync.aligned.m16n8k16.row.col.f32.bf16.bf16.f32 {%0,%1,%2,%3},{%4,%5,%6,%7},{%8,%9},{%10,%11,%12,%13};"
               : "=f"(d[0]), "=f"(d[1]), "=f"(d[2]), "=f"(d[3])
               : "r"(a0), "r"(a1), "r"(a2), "r"(a3), "r"(b0), "r"(b1), "f"(c[0]), "f"(c[1]), "f"(c[2]), "f"(c[3]));
}
__device__ __forceinline__ void mma_h(float (&d)[4], const uint32_t (&a)[4], uint32_t b0, uint32_t b1) {
  asm volatile("mma.sync.aligned.m16n8k16.row.col.f32.f16.f16.f32 {%0,%1,%2,%3},{%4,%5,%6,%7},{%8,%9},{%0,%1,%2,%3};"
               : "+f"(d[0]), "+f"(d[1]), "+f"(d[2]), "+f"(d[3]) : "r"(a[0]), "r"(a[1]), "r"(a[2]), "r"(a[3]), "r"(b0), "r"(b1));
}
__device__ __forceinline__ void mma0(float& d0, float& d1, float& d2, float& d3, uint32_t a0, uint32_t a1, uint32_t a2,
                                     uint32_t a3, uint32_t b0, uint32_t b1) {
  asm volatile("mma.sync.aligned.m16n8k16.row.col.f32.bf16.bf16.f32 {%0,%1,%2,%3},{%4,%5,%6,%7},{%8,%9},{%10,%10,%10,%10};"
               : "=f"(d0), "=f"(d1), "=f"(d2), "=f"(d3)
               : "r"(a0), "r"(a1), "r"(a2), "r"(a3), "r"(b0), "r"(b1), "f"(0.f));
}
__device__ __forceinline__ uint32_t pack_bf(float lo, float hi) {
  uint32_t r;
  asm("cvt.rn.bf16x2.f32 %0, %1, %2;" : "=r"(r) : "f"(hi), "f"(lo));
  return r;
}
__device__ __forceinline__ float bf_lo(uint32_t w) { return __uint_as_float(w << 16); }
__device__ __forceinline__ float bf_hi(uint32_t w) { return __uint_as_float(w & 0xffff0000u); }
__device__ __forceinline__ float bf_round(float x) { return __bfloat162float(__float2bfloat16_rn(x)); }
__device__ __forceinline__ uint32_t bmax2(uint32_t a, uint32_t b) {
  uint32_t r; asm("max.bf16x2 %0, %1, %2;" : "=r"(r) : "r"(a), "r"(b)); return r;
}
__device__ __forceinline__ uint32_t bmin2(uint32_t a, uint32_t b) {
  uint32_t r; asm("min.bf16x2 %0, %1, %2;" : "=r"(r) : "r"(a), "r"(b)); return r;
}
__device__ __forceinline__ float ex2(float x) { float r; asm("ex2.approx.ftz.f32 %0, %1;" : "=f"(r) : "f"(x)); return r; }
__device__ __forceinline__ float rcp(float x) { float r; asm("rcp.approx.ftz.f32 %0, %1;" : "=f"(r) : "f"(x)); return r; }
__device__ __forceinline__ void ldsm4(uint32_t (&r)[4], uint32_t a) {
  asm volatile("ldmatrix.sync.aligned.m8n8.x4.shared.b16 {%0,%1,%2,%3}, [%4];"
               : "=r"(r[0]), "=r"(r[1]), "=r"(r[2]), "=r"(r[3]) : "r"(a) : "memory");
}
__device__ __forceinline__ void ldsm4t(uint32_t (&r)[4], uint32_t a) {
  asm volatile("ldmatrix.sync.aligned.m8n8.x4.trans.shared.b16 {%0,%1,%2,%3}, [%4];"
               : "=r"(r[0]), "=r"(r[1]), "=r"(r[2]), "=r"(r[3]) : "r"(a) : "memory");
}
__device__ __forceinline__ void stsm4(uint32_t a, uint32_t r0, uint32_t r1, uint32_t r2, uint32_t r3) {
  asm volatile("stmatrix.sync.aligned.m8n8.x4.shared.b16 [%0], {%1,%2,%3,%4};"
               ::"r"(a), "r"(r0), "r"(r1), "r"(r2), "r"(r3) : "memory");
}
__device__ __forceinline__ uint32_t lds32(uint32_t a) {
  uint32_t r; asm volatile("ld.shared.u32 %0, [%1];" : "=r"(r) : "r"(a) : "memory"); return r;
}
__device__ __forceinline__ uint32_t lds16(uint32_t a) {
  uint32_t r; asm volatile("{\n.reg .u16 h;\nld.shared.u16 h, [%1];\ncvt.u32.u16 %0, h;\n}\n" : "=r"(r) : "r"(a) : "memory"); return r;
}
__device__ __forceinline__ uint2 lds64(uint32_t a) {
  uint2 r; asm volatile("ld.shared.v2.u32 {%0,%1}, [%2];" : "=r"(r.x), "=r"(r.y) : "r"(a) : "memory"); return r;
}
__device__ __forceinline__ uint4 lds128(uint32_t a) {
  uint4 r;
  asm volatile("ld.shared.v4.u32 {%0,%1,%2,%3}, [%4];" : "=r"(r.x), "=r"(r.y), "=r"(r.z), "=r"(r.w) : "r"(a) : "memory");
  return r;
}
__device__ __forceinline__ void sts32(uint32_t a, uint32_t v) { asm volatile("st.shared.u32 [%0], %1;" ::"r"(a), "r"(v) : "memory"); }
__device__ __forceinline__ void sts16(uint32_t a, uint32_t v) {
  asm volatile("{\n.reg .u16 h;\ncvt.u16.u32 h, %1;\nst.shared.u16 [%0], h;\n}\n" ::"r"(a), "r"(v) : "memory");
}
__device__ __forceinline__ void sts64(uint32_t a, uint32_t x, uint32_t y) {
  asm volatile("st.shared.v2.u32 [%0], {%1,%2};" ::"r"(a), "r"(x), "r"(y) : "memory");
}
__device__ __forceinline__ void sts128(uint32_t a, uint32_t x, uint32_t y, uint32_t z, uint32_t w) {
  asm volatile("st.shared.v4.u32 [%0], {%1,%2,%3,%4};" ::"r"(a), "r"(x), "r"(y), "r"(z), "r"(w) : "memory");
}
__device__ __forceinline__ uint4 ld_x(const uint4* p) {
  uint4 r;
  asm volatile("{\n.reg .b128 t;\nld.relaxed.gpu.global.b128 t, [%4];\nmov.b128 {%0,%1,%2,%3}, t;\n}\n"
               : "=r"(r.x), "=r"(r.y), "=r"(r.z), "=r"(r.w) : "l"(p) : "memory");
  return r;
}
__device__ __forceinline__ uint32_t ld_x32(const uint32_t* p) {
  uint32_t r; asm volatile("ld.relaxed.gpu.global.u32 %0, [%1];" : "=r"(r) : "l"(p) : "memory"); return r;
}
__device__ __forceinline__ void st_x(uint4* p, uint32_t x, uint32_t y, uint32_t z, uint32_t w) {
  asm volatile("{\n.reg .b128 t;\nmov.b128 t, {%1,%2,%3,%4};\nst.relaxed.gpu.global.b128 [%0], t;\n}\n"
               ::"l"(p), "r"(x), "r"(y), "r"(z), "r"(w) : "memory");
}
__device__ __forceinline__ void st_x32(uint32_t* p, uint32_t x) {
  asm volatile("st.relaxed.gpu.global.u32 [%0], %1;" ::"l"(p), "r"(x) : "memory");
}
__device__ __forceinline__ uint32_t nz(uint32_t w) { return max(w, 1u); }
__device__ __forceinline__ uint32_t fu(float x) { return __float_as_uint(x); }
__device__ __forceinline__ float uf(uint32_t x) { return __uint_as_float(x); }

__device__ __forceinline__ void wgmma_ss_n96(float (&d)[48], uint64_t da, uint64_t db, int sc) {
  asm volatile("{\n.reg .pred p;\nsetp.ne.b32 p, %50, 0;\n"
      "wgmma.mma_async.sync.aligned.m64n96k16.f32.bf16.bf16 "
      "{%0,%1,%2,%3,%4,%5,%6,%7,%8,%9,%10,%11,%12,%13,%14,%15,%16,%17,%18,%19,%20,%21,%22,%23,%24,%25,%26,%27,%28,%29,%30,%31,%32,%33,%34,%35,%36,%37,%38,%39,%40,%41,%42,%43,%44,%45,%46,%47}, "
      "%48, %49, p, 1, 1, 0, 1;\n}\n"
      : "+f"(d[0]), "+f"(d[1]), "+f"(d[2]), "+f"(d[3]), "+f"(d[4]), "+f"(d[5]), "+f"(d[6]), "+f"(d[7]),
        "+f"(d[8]), "+f"(d[9]), "+f"(d[10]), "+f"(d[11]), "+f"(d[12]), "+f"(d[13]), "+f"(d[14]), "+f"(d[15]),
        "+f"(d[16]), "+f"(d[17]), "+f"(d[18]), "+f"(d[19]), "+f"(d[20]), "+f"(d[21]), "+f"(d[22]), "+f"(d[23]),
        "+f"(d[24]), "+f"(d[25]), "+f"(d[26]), "+f"(d[27]), "+f"(d[28]), "+f"(d[29]), "+f"(d[30]), "+f"(d[31]),
        "+f"(d[32]), "+f"(d[33]), "+f"(d[34]), "+f"(d[35]), "+f"(d[36]), "+f"(d[37]), "+f"(d[38]), "+f"(d[39]),
        "+f"(d[40]), "+f"(d[41]), "+f"(d[42]), "+f"(d[43]), "+f"(d[44]), "+f"(d[45]), "+f"(d[46]), "+f"(d[47])
      : "l"(da), "l"(db), "r"(sc));
}

__device__ __forceinline__ void wgmma_ss_n128(float (&d)[64], uint64_t da, uint64_t db, int sc) {
  asm volatile("{\n.reg .pred p;\nsetp.ne.b32 p, %66, 0;\n"
      "wgmma.mma_async.sync.aligned.m64n128k16.f32.bf16.bf16 "
      "{%0,%1,%2,%3,%4,%5,%6,%7,%8,%9,%10,%11,%12,%13,%14,%15,%16,%17,%18,%19,%20,%21,%22,%23,%24,%25,%26,%27,%28,%29,%30,%31,%32,%33,%34,%35,%36,%37,%38,%39,%40,%41,%42,%43,%44,%45,%46,%47,%48,%49,%50,%51,%52,%53,%54,%55,%56,%57,%58,%59,%60,%61,%62,%63}, "
      "%64, %65, p, 1, 1, 0, 1;\n}\n"
      : "+f"(d[0]), "+f"(d[1]), "+f"(d[2]), "+f"(d[3]), "+f"(d[4]), "+f"(d[5]), "+f"(d[6]), "+f"(d[7]),
        "+f"(d[8]), "+f"(d[9]), "+f"(d[10]), "+f"(d[11]), "+f"(d[12]), "+f"(d[13]), "+f"(d[14]), "+f"(d[15]),
        "+f"(d[16]), "+f"(d[17]), "+f"(d[18]), "+f"(d[19]), "+f"(d[20]), "+f"(d[21]), "+f"(d[22]), "+f"(d[23]),
        "+f"(d[24]), "+f"(d[25]), "+f"(d[26]), "+f"(d[27]), "+f"(d[28]), "+f"(d[29]), "+f"(d[30]), "+f"(d[31]),
        "+f"(d[32]), "+f"(d[33]), "+f"(d[34]), "+f"(d[35]), "+f"(d[36]), "+f"(d[37]), "+f"(d[38]), "+f"(d[39]),
        "+f"(d[40]), "+f"(d[41]), "+f"(d[42]), "+f"(d[43]), "+f"(d[44]), "+f"(d[45]), "+f"(d[46]), "+f"(d[47]),
        "+f"(d[48]), "+f"(d[49]), "+f"(d[50]), "+f"(d[51]), "+f"(d[52]), "+f"(d[53]), "+f"(d[54]), "+f"(d[55]),
        "+f"(d[56]), "+f"(d[57]), "+f"(d[58]), "+f"(d[59]), "+f"(d[60]), "+f"(d[61]), "+f"(d[62]), "+f"(d[63])
      : "l"(da), "l"(db), "r"(sc));
}

__device__ __forceinline__ void wgmma_ss_n40(float (&d)[20], uint64_t da, uint64_t db, int sc) {
  asm volatile("{\n.reg .pred p;\nsetp.ne.b32 p, %22, 0;\n"
      "wgmma.mma_async.sync.aligned.m64n40k16.f32.bf16.bf16 "
      "{%0,%1,%2,%3,%4,%5,%6,%7,%8,%9,%10,%11,%12,%13,%14,%15,%16,%17,%18,%19}, "
      "%20, %21, p, 1, 1, 1, 1;\n}\n"
      : "+f"(d[0]), "+f"(d[1]), "+f"(d[2]), "+f"(d[3]), "+f"(d[4]), "+f"(d[5]), "+f"(d[6]), "+f"(d[7]),
        "+f"(d[8]), "+f"(d[9]), "+f"(d[10]), "+f"(d[11]), "+f"(d[12]), "+f"(d[13]), "+f"(d[14]), "+f"(d[15]),
        "+f"(d[16]), "+f"(d[17]), "+f"(d[18]), "+f"(d[19])
      : "l"(da), "l"(db), "r"(sc));
}

__device__ __forceinline__ void wgmma_rs_n8(float (&d)[4], const uint4& a, uint64_t db, int sc) {
  asm volatile("{\n.reg .pred p;\nsetp.ne.b32 p, %9, 0;\n"
      "wgmma.mma_async.sync.aligned.m64n8k16.f32.bf16.bf16 "
      "{%0,%1,%2,%3}, "
      "{%4,%5,%6,%7}, %8, p, 1, 1, 1;\n}\n"
      : "+f"(d[0]), "+f"(d[1]), "+f"(d[2]), "+f"(d[3])
      : "r"(a.x), "r"(a.y), "r"(a.z), "r"(a.w), "l"(db), "r"(sc));
}

__device__ __forceinline__ void wgmma_rs_n16(float (&d)[8], const uint4& a, uint64_t db, int sc) {
  asm volatile("{\n.reg .pred p;\nsetp.ne.b32 p, %13, 0;\n"
      "wgmma.mma_async.sync.aligned.m64n16k16.f32.bf16.bf16 "
      "{%0,%1,%2,%3,%4,%5,%6,%7}, "
      "{%8,%9,%10,%11}, %12, p, 1, 1, 1;\n}\n"
      : "+f"(d[0]), "+f"(d[1]), "+f"(d[2]), "+f"(d[3]), "+f"(d[4]), "+f"(d[5]), "+f"(d[6]), "+f"(d[7])
      : "r"(a.x), "r"(a.y), "r"(a.z), "r"(a.w), "l"(db), "r"(sc));
}

__device__ __forceinline__ void wgmma_rs_n24(float (&d)[12], const uint4& a, uint64_t db, int sc) {
  asm volatile("{\n.reg .pred p;\nsetp.ne.b32 p, %17, 0;\n"
      "wgmma.mma_async.sync.aligned.m64n24k16.f32.bf16.bf16 "
      "{%0,%1,%2,%3,%4,%5,%6,%7,%8,%9,%10,%11}, "
      "{%12,%13,%14,%15}, %16, p, 1, 1, 1;\n}\n"
      : "+f"(d[0]), "+f"(d[1]), "+f"(d[2]), "+f"(d[3]), "+f"(d[4]), "+f"(d[5]), "+f"(d[6]), "+f"(d[7]),
        "+f"(d[8]), "+f"(d[9]), "+f"(d[10]), "+f"(d[11])
      : "r"(a.x), "r"(a.y), "r"(a.z), "r"(a.w), "l"(db), "r"(sc));
}

struct Params {
  const __nv_bfloat16 *logA, *Aim, *Cre, *Cim, *logdt, *Dskip, *x, *wphi, *wo;
  __nv_bfloat16* out;
  uint4* xs;
  long long* ts;
};

__device__ __forceinline__ uint4 tr_row(const uint4 (&v)[8], int i) {
  uint32_t o[4];
#pragma unroll
  for (int m = 0; m < 4; m++) {
    const uint4 &ra = v[2 * m], &rb = v[2 * m + 1];
    const int k = i >> 1;
    const uint32_t xa = k == 0 ? ra.x : k == 1 ? ra.y : k == 2 ? ra.z : ra.w;
    const uint32_t xb = k == 0 ? rb.x : k == 1 ? rb.y : k == 2 ? rb.z : rb.w;
    o[m] = __byte_perm(xa, xb, (i & 1) ? 0x7632 : 0x5410);
  }
  return make_uint4(o[0], o[1], o[2], o[3]);
}

struct cpx { float r, i; };
__device__ __forceinline__ cpx csq(cpx a) { return {a.r * a.r - a.i * a.i, 2.f * (a.r * a.i)}; }
__device__ __forceinline__ cpx polar(float e, float t) {
  const float m = ex2(e);
  return {m * __cosf(t), m * __sinf(t)};
}

struct KgenRaw { uint32_t la, ai, cr, ci, ldt; };
__device__ __forceinline__ KgenRaw kgen_load(const Params& P, int d, int unit, int lane, int on) {
  const int o = d * 64 + unit * 32 + lane;
  KgenRaw r = {0, 0, 0, 0, 0};
  asm volatile("{\n.reg .pred p;\nsetp.ne.b32 p, %10, 0;\n@p ld.global.nc.u32 %0, [%5];\n@p ld.global.nc.u32 %1, [%6];\n"
               "@p ld.global.nc.u32 %2, [%7];\n@p ld.global.nc.u32 %3, [%8];\n@p ld.global.nc.u16 %4, [%9];\n}\n"
               : "+r"(r.la), "+r"(r.ai), "+r"(r.cr), "+r"(r.ci), "+r"(r.ldt)
               : "l"((const uint32_t*)P.logA + o), "l"((const uint32_t*)P.Aim + o), "l"((const uint32_t*)P.Cre + o),
                 "l"((const uint32_t*)P.Cim + o), "l"(P.logdt + d), "r"(on));
  return r;
}
struct hc { __half2 r, i; };
struct cpx2 { cpx a, b; };
__device__ __forceinline__ cpx2 csq2(const cpx2& v) { return {csq(v.a), csq(v.b)}; }
__device__ __forceinline__ hc toh(const cpx2& v) { return {__floats2half2_rn(v.a.r, v.b.r), __floats2half2_rn(v.a.i, v.b.i)}; }
__device__ __forceinline__ hc hmul(const hc& z, const hc& w) {
  return {__hfma2(z.r, w.r, __hneg2(__hmul2(z.i, w.i))), __hfma2(z.r, w.i, __hmul2(z.i, w.r))};
}
__device__ __forceinline__ hc hmulc(const hc& z, const hc& w) {
  return {__hfma2(z.r, w.r, __hmul2(z.i, w.i)), __hfma2(z.i, w.r, __hneg2(__hmul2(z.r, w.i)))};
}
__device__ __forceinline__ uint32_t hu(__half2 v) { return *(const uint32_t*)&v; }
__device__ __forceinline__ __half2 uh(uint32_t v) { return *(const __half2*)&v; }

struct KgenAddr { uint32_t sa[2], ld[5][4]; };
__device__ __forceinline__ KgenAddr kgen_addr(int lane, uint32_t buf) {
  KgenAddr a;
  a.sa[0] = buf + (lane & 7) * 128 + ((((lane >> 3) ^ lane) & 7) << 4);
  a.sa[1] = a.sa[0] ^ 64;
  const int q = lane >> 4;
  const uint32_t b = buf + ((lane >> 3) & 1) * 1024 + q * 128;
  const int e[5] = {lane & 7, 0, 1, 2 + (lane & 1), 4 + (lane & 3)};
#pragma unroll
  for (int i = 0; i < 20; i++) {
    a.ld[i >> 2][i & 3] = b + ((e[i >> 2] ^ q ^ (2 * (i & 3))) << 4);
    asm volatile("" : "+r"(a.ld[i >> 2][i & 3]));
  }
  asm volatile("" : "+r"(a.sa[0]), "+r"(a.sa[1]));
  return a;
}
__device__ __forceinline__ void kgen_unit(const KgenRaw& r, const KgenAddr& ad, uint32_t zero, float (&k)[5][4], float& k2048, float& sc) {
  const float dt = bf_round(expf(bf_lo(r.ldt)));
  const uint32_t ar = pack_bf(ex2(bf_lo(r.la) * 1.4426950408889634f), ex2(bf_hi(r.la) * 1.4426950408889634f));
  const float ca = dt * -1.4426950408889634f, a0 = bf_lo(ar) * ca, a1 = bf_hi(ar) * ca;
  const float f0 = bf_lo(r.ai) * dt, f1 = bf_hi(r.ai) * dt;
  const float r0 = f0 * 20.21267777267071f, r1 = f1 * 20.21267777267071f;
  const uint32_t cm = __vmaxu2(r.cr & 0x7fff7fffu, r.ci & 0x7fff7fffu);
  const uint32_t ex = min(max(__reduce_max_sync(0xffffffffu, max(cm >> 16, cm & 0xffffu)) >> 7, 1u), 253u);
  const float cs = uf((254u - ex) << 23);
  sc = 2.f * dt * uf(ex << 23);
  const cpx2 C = {{bf_lo(r.cr) * cs, bf_lo(r.ci) * -cs}, {bf_hi(r.cr) * cs, bf_hi(r.ci) * -cs}};
  auto put = [&](const hc (&v)[8]) {
    stsm4(ad.sa[0], hu(v[0].r), hu(v[1].r), hu(v[2].r), hu(v[3].r));
    stsm4(ad.sa[0] + 1024, hu(v[0].i), hu(v[1].i), hu(v[2].i), hu(v[3].i));
    stsm4(ad.sa[1], hu(v[4].r), hu(v[5].r), hu(v[6].r), hu(v[7].r));
    stsm4(ad.sa[1] + 1024, hu(v[4].i), hu(v[5].i), hu(v[6].i), hu(v[7].i));
    __syncwarp();
  };
  auto get = [&](uint32_t (&o)[4][4], const uint32_t (&a)[4]) {
#pragma unroll
    for (int i = 0; i < 4; i++) ldsm4(o[i], a[i] + i * 256);
  };
  auto at = [](const uint32_t (&o)[4][4], int s) { return hc{uh(o[s >> 1][2 * (s & 1)]), uh(o[s >> 1][2 * (s & 1) + 1])}; };
  uint32_t A[8][4];
  auto tile = [&](int j, const uint32_t (&B)[4][4]) {
    k[j][0] = k[j][1] = k[j][2] = k[j][3] = 0.f;
#pragma unroll
    for (int s = 0; s < 8; s++) mma_h(k[j], A[s], B[s >> 1][2 * (s & 1)], B[s >> 1][2 * (s & 1) + 1]);
  };
  const cpx2 w1 = {polar(a0, f0), polar(a1, f1)};
  const cpx2 w127 = {polar(a0 * 127.f, (r0 - rintf(r0)) * 6.283185307179586f), polar(a1 * 127.f, (r1 - rintf(r1)) * 6.283185307179586f)};
  const cpx2 w2 = csq2(w1), w4 = csq2(w2);
  uint32_t T0[4][4], X[4][4], M[3][4][4];
  {
    hc t[8];
    t[0] = {uh(0x3C003C00u), uh(0u)}; t[1] = toh(w1); t[2] = toh(w2); t[4] = toh(w4);
    t[3] = hmul(t[1], t[2]); t[5] = hmul(t[1], t[4]); t[6] = hmul(t[2], t[4]); t[7] = hmul(t[3], t[4]);
    put(t); get(T0, ad.ld[0]);
  }
  SPLIT();
  const cpx2 w8 = csq2(w4), w16 = csq2(w8), w32 = csq2(w16), w64 = csq2(w32);
  {
    const hc m8 = toh(w8), m16 = toh(w16), m32 = toh(w32);
    hc a[8];
    a[0] = toh(C); a[1] = hmulc(a[0], m8);
    a[2] = hmulc(a[0], m16); a[3] = hmulc(a[1], m16);
#pragma unroll
    for (int i = 0; i < 4; i++) a[4 + i] = hmulc(a[i], m32);
    put(a); get(X, ad.ld[0]);
  }
  SPLIT();
    const cpx2 w128 = {{w127.a.r * w1.a.r - w127.a.i * w1.a.i, w127.a.r * w1.a.i + w127.a.i * w1.a.r},
                     {w127.b.r * w1.b.r - w127.b.i * w1.b.i, w127.b.r * w1.b.i + w127.b.i * w1.b.r}};
  const cpx2 w256 = csq2(w128), w512 = csq2(w256);
  const hc m128 = toh(w128), m256 = toh(w256), m512 = toh(w512);
  {
    const hc m254 = toh(csq2(w127)), m127 = toh(w127);
    hc m[8];
    m[0] = toh(w64); m[1] = m128; m[2] = m256; m[3] = hmul(m127, m256);
    m[4] = m512; m[5] = hmul(m127, m512); m[6] = hmul(m[4], m254); m[7] = hmul(m[5], m254);
    put(m);
    get(M[0], ad.ld[1]);
#pragma unroll
    for (int s = 0; s < 8; s++) {
      const hc z = at(X, s), y = hmulc(z, at(M[0], s));
      A[s][0] = hu(z.r) + zero; A[s][1] = hu(y.r); A[s][2] = hu(z.i) + zero; A[s][3] = hu(y.i);
    }
#pragma unroll
    for (int i = 0; i < 3; i++) get(M[i], ad.ld[i + 2]);
  }
  SPLIT();
  tile(0, T0);
  const cpx2 w1024 = csq2(w512), we = csq2(w1024);
  {
    hc t[8];
    t[0] = toh(w1024); t[1] = hmul(t[0], m128);
    t[2] = hmul(t[0], m256); t[3] = hmul(t[1], m256);
#pragma unroll
    for (int i = 0; i < 4; i++) t[4 + i] = hmul(t[i], m512);
    put(t); get(X, ad.ld[0]);
  }
  k2048 = (C.a.r * we.a.r + C.a.i * we.a.i + C.b.r * we.b.r + C.b.i * we.b.i) * sc;
#pragma unroll
  for (int j = 1; j < 5; j++) k[j][0] = k[j][1] = k[j][2] = k[j][3] = 0.f;
#pragma unroll
  for (int s = 0; s < 8; s++) {
#pragma unroll
    for (int j = 0; j < 3; j++) {
      const hc y = hmul(at(T0, s), at(M[j], s));
      mma_h(k[1 + j], A[s], hu(y.r), hu(y.i));
    }
    mma_h(k[4], A[s], X[s >> 1][2 * (s & 1)], X[s >> 1][2 * (s & 1) + 1]);
  }
}

__device__ __forceinline__ void build_tables(uint32_t tb, int lane, float (&k)[5][4], float k2048) {
  const int g = lane >> 2, c = lane & 3;
  const uint32_t kc = tb + T_KC + 16;
  {
    const uint32_t a0 = kc + 16 * g + 4 * c, a2 = kc + 2 * (256 + 4 * g + c);
    const uint32_t a3 = kc + 2 * (384 + 2 * g + 64 * (c & 1) + (c >> 1)), a4 = kc + 2 * (512 + g + 32 * c);
#pragma unroll
    for (int r = 0; r < 2; r++) {
      sts32(a0 + 128 * r, pack_bf(k[0][2 * r], k[0][2 * r + 1]));
      sts32(a0 + 128 * r + 256, pack_bf(k[1][2 * r], k[1][2 * r + 1]));
      const uint32_t w2 = pack_bf(k[2][2 * r], k[2][2 * r + 1]);
      const uint32_t w3 = pack_bf(k[3][2 * r], k[3][2 * r + 1]);
      const uint32_t w4 = pack_bf(k[4][2 * r], k[4][2 * r + 1]);
      sts16(a2 + 64 * r, w2); sts16(a2 + 64 * r + 128, w2 >> 16);
      sts16(a3 + 32 * r, w3); sts16(a3 + 32 * r + 64, w3 >> 16);
      sts16(a4 + 16 * r, w4); sts16(a4 + 16 * r + 32, w4 >> 16);
    }
  }
  if (lane == 0) { sts16(kc + 2 * 640, pack_bf(k2048, 0.f)); sts32(kc - 4, 0); }
  __syncwarp();
  const uint32_t td = tb + T_D + 32;
#pragma unroll
  for (int hf = 0; hf < 2; hf++) {
    const uint2 v = lds64(kc + 256 * hf + 8 * lane);
    const uint32_t pv = lds32(kc + 256 * hf + 8 * lane - 4);
    sts128(td + 512 * hf + 16 * lane, __byte_perm(v.x, pv, 0x7610), __byte_perm(v.x, v.x, 0x1032), __byte_perm(v.y, v.x, 0x7610),
           __byte_perm(v.y, v.y, 0x1032));
  }
#pragma unroll
  for (int hf = 0; hf < 2; hf++) {
    const uint32_t v = lds32(kc + 512 + 128 * hf + 4 * lane), nx = lds32(kc + 516 + 128 * hf + 4 * lane);
    uint32_t w0 = __byte_perm(v, v, 0x1010);
    const uint32_t w1 = w0;
    if (hf == 0) { const uint32_t pv = lds32(kc + 508); if (lane == 0) w0 = __byte_perm(v, pv, 0x7610); }
    sts128(td + 1024 + 512 * hf + 16 * lane, w0, w1, __byte_perm(v, v, 0x1032), __byte_perm(nx, v, 0x7610));
  }
  {
    const uint32_t kk = lds16(kc + 2 * 384);
    const uint32_t w = lane < 3 ? (kk | (kk << 16)) : (lane == 3 ? (kk << 16) : 0u);
    if (lane < 24) sts32(td + 4 * (lane < 16 ? 512 + lane : lane - 24), w);
    const uint32_t lo_ = lds16(kc + 2 * 511), le_ = lds16(kc + 2 * 512);
    const uint32_t ja = tb + T_5 + (lane < 16 ? 4 * lane : 256 + 4 * lane);
    sts32(ja, lane == 16 ? (le_ << 16) : 0u);
    sts32(ja + 384, lane == 16 ? (lo_ << 16) : 0u);
    sts32(tb + (lane < 16 ? T_7 : T_9 - 64) + 4 * lane, 0u);
  }
#pragma unroll
  for (int s = 0; s < 2; s++) {
    const uint32_t b = kc + 2 * (s ? 512 : 384) + 8 * lane;
    const uint2 v = lds64(b);
    uint32_t em = lds16(b - 2), e0 = v.x;
    const uint32_t e4 = lds16(b + 8);
    if (lane == 0) { em = 0; e0 = 0; }
    sts64(tb + (s ? T_7 : T_3) + 64 + 8 * lane, __byte_perm(v.x, em, 0x5432), __byte_perm(v.y, v.x, 0x7632));
    sts64(tb + (s ? T_9 : T_5) + 64 + 8 * lane, __byte_perm(v.y, e0, 0x5410), __byte_perm(e4, v.y, 0x5410));
  }
  __syncwarp();
}

__device__ __forceinline__ uint32_t box2w(int lo, int n, int o) {
  return ((unsigned)(o - lo) < (unsigned)n ? 0x3F80u : 0u) | ((unsigned)(o + 1 - lo) < (unsigned)n ? 0x3F800000u : 0u);
}

__device__ __forceinline__ void conv_channel(uint32_t ub, uint32_t tb, int lane, uint4* ydst) {
  const int g = lane >> 2, c = lane & 3, x = g - 2 * c;
  const int mi = lane >> 3;
  const uint32_t qa = ub + U_PAD + 16 * (lane & 7) + ((mi == 0 || mi == 3) ? U_ODD : 0) - (mi == 0 ? 16 : 0);
  const uint32_t hb = ub + U_PAD + (mi & 1) * U_ODD + 16 * ((lane >> 4) + (lane & 7)) - 16;
  const uint32_t kv = lds16(tb + T_KC + 16 + 2 * 512);
  const int oh = c < 2 ? 8 + 2 * c : 2 * c - 8, og = c < 3 ? 2 * c : -10;
  uint32_t bx[4] = {box2w(g - 4, 9, 2 * c), box2w(g - 3, 7, 2 * c), box2w(g - 4, 9, oh), box2w(g - 3, 7, oh)};
  uint32_t by[4] = {box2w(g - 10, 5, 2 * c - 8), box2w(g - 5, 3, 2 * c - 8), box2w(g - 10, 5, og), box2w(g - 5, 3, og)};
  uint32_t lb0 = ((unsigned)(x + 5) < 2u ? kv : 0u) | ((unsigned)(x + 4) < 2u ? kv << 16 : 0u);
  uint32_t lb1 = ((unsigned)(x - 3) < 2u ? kv : 0u) | ((unsigned)(x - 4) < 2u ? kv << 16 : 0u);
  const int q0 = g - 1, q1 = c < 3 ? g : g - 2;
  uint32_t y0a = ub + U_PAD + (q0 & 1) * U_ODD + 16 * (q0 >> 1) + 4 * c;
  uint32_t y1a = ub + U_PAD + (q1 & 1) * U_ODD + 16 * (q1 >> 1) + 4 * c;
#pragma unroll
  for (int i = 0; i < 4; i++) asm volatile("" : "+r"(bx[i]), "+r"(by[i]));
  asm volatile("" : "+r"(lb0), "+r"(lb1), "+r"(y0a), "+r"(y1a));
  mbar_wait(BAR(MB_UFULL));
  mbar_spin(BAR(MB_EMPTY + 15));
  TS(36);
  float acc[16][4];
  {
    uint32_t z09[8], z07[8], zm9[8], zm7[8];
#pragma unroll
    for (int i = 0; i < 8; i++) {
      uint32_t h[4];
      ldsm4(h, hb + 128 * i);
      float y0, y1, y2, y3, w0, w1, w2, w3;
      mma0(y0, y1, y2, y3, bx[0], bx[1], bx[2], bx[3], h[2], c < 2 ? h[3] : h[1]);
      mma0(w0, w1, w2, w3, bx[0], bx[1], bx[2], bx[3], h[1], c < 2 ? h[2] : h[0]);
      z09[i] = pack_bf(y0, y1); z07[i] = pack_bf(y2, y3);
      zm9[i] = pack_bf(w0, w1); zm7[i] = pack_bf(w2, w3);
    }
  uint32_t f3[3][4][4];
  {
    const uint32_t fa = tb + T_7 + 4 * (16 + x);
#pragma unroll
    for (int tt = 0; tt < 3; tt++)
#pragma unroll
      for (int D = 0; D < 4; D++) {
        const uint32_t a = fa + (tt == 0 ? 316 : (tt == 1 ? 320 : 0)) + 64 * D;
        f3[tt][D][0] = lds32(a); f3[tt][D][1] = lds32(a + 32); f3[tt][D][2] = lds32(a - 32); f3[tt][D][3] = lds32(a);
      }
  }
    SPLIT();
    nb_sync(NB_GATE, 256);
    SPLIT();
    float a[4][2][4];
#pragma unroll
    for (int kap = 0; kap < 4; kap++)
#pragma unroll
      for (int sg = 0; sg < 2; sg++)
#pragma unroll
        for (int bk = 3; bk >= kap; bk--) {
          const uint32_t(&q0_)[4] = f3[sg ? 2 : 0][bk - kap];
          const uint32_t(&q1_)[4] = f3[sg ? 2 : 1][bk - kap];
          float(&a0)[4] = a[bk][0];
          float(&a1)[4] = a[bk][1];
          if (sg == 0 && kap == 0) {
            mma0(a0[0], a0[1], a0[2], a0[3], q0_[0], q0_[1], q0_[2], q0_[3], z09[0], z09[1]);
            mma0(a1[0], a1[1], a1[2], a1[3], q1_[0], q1_[1], q1_[2], q1_[3], zm9[0], zm9[1]);
          } else {
            mma(a0[0], a0[1], a0[2], a0[3], q0_[0], q0_[1], q0_[2], q0_[3], sg ? zm7[2 * kap] : z09[2 * kap], sg ? zm7[2 * kap + 1] : z09[2 * kap + 1]);
            mma(a1[0], a1[1], a1[2], a1[3], q1_[0], q1_[1], q1_[2], q1_[3], sg ? z07[2 * kap] : zm9[2 * kap], sg ? z07[2 * kap + 1] : zm9[2 * kap + 1]);
          }
        }
    SPLIT();
#pragma unroll
    for (int i = 0; i < 8; i++) {
      uint32_t h[4];
      ldsm4(h, qa + 128 * i);
      const float ci[4] = {a[i >> 1][0][2 * (i & 1)], a[i >> 1][0][2 * (i & 1) + 1], a[i >> 1][1][2 * (i & 1)], a[i >> 1][1][2 * (i & 1) + 1]};
      mmac(acc[8 + i], h[0], h[1], h[2], h[3], lb0, lb1, ci);
    }
  }
  TS(44);
  {
    uint2 a5[10], a3[10];
    const uint32_t aa = tb + T_5 + 4 * (8 + 2 * g - 2 * c);
#pragma unroll
    for (int m = 0; m < 10; m++) { a5[m] = lds64(aa + 32 * m); a3[m] = lds64(aa + 384 + 32 * m); }
    uint32_t x5[12][2], x3[12][2];
    auto ygen = [&](int kap) {
#pragma unroll
      for (int hh = 0; hh < 2; hh++) {
        float y0, y1, y2, y3;
        mma0(y0, y1, y2, y3, by[0], by[1], by[2], by[3], lds32(y0a + 128 * kap + 64 * hh), lds32(y1a + 128 * kap + 64 * hh));
        x5[kap][hh] = pack_bf(y0, y1);
        x3[kap][hh] = pack_bf(y2, y3);
      }
    };
    ygen(11); ygen(10); ygen(9); ygen(8);
#pragma unroll
    for (int kap = 11; kap >= 0; kap--) {
      if (kap >= 4) ygen(kap - 4);
#pragma unroll
      for (int sg = 0; sg < 2; sg++)
#pragma unroll
        for (int i = 4; i >= 0; i--) {
          const int be = kap + 4 + i;
          if (be <= 15) {
            const uint2 &hi = sg ? a3[2 * i + 1] : a5[2 * i + 1], &lo = sg ? a3[2 * i] : a5[2 * i];
            const uint32_t b0 = sg ? x3[kap][0] : x5[kap][0], b1 = sg ? x3[kap][1] : x5[kap][1];
            if (be < 8 && i == 0 && sg == 0) mma0(acc[be][0], acc[be][1], acc[be][2], acc[be][3], hi.x, hi.y, lo.x, lo.y, b0, b1);
            else mma(acc[be][0], acc[be][1], acc[be][2], acc[be][3], hi.x, hi.y, lo.x, lo.y, b0, b1);
          }
        }
    }
  }
  TS(45);
  {
    const uint32_t st = tb + T_ST + lane * 8;
#pragma unroll
    for (int be = 4; be < 12; be++) sts64(st + 256 * be, pack_bf(acc[be][0], acc[be][1]), pack_bf(acc[be][2], acc[be][3]));
    SPLIT();
    uint32_t F[66], qd[8][4];
    const uint32_t fa = tb + T_D + 32 + 4 * x;
#pragma unroll
    for (int i = 0; i < 32; i++) {
      const int s = 120 - (i >> 2) - 8 * (i & 3);
      uint32_t(&q)[4] = qd[i & 7];
      ldsm4(q, qa + 16 * s);
      const int m = 16 * (i & 3) + 2 * (i >> 2);
      F[m] = lds32(fa + 32 * m); F[m + 1] = lds32(fa + 32 * m + 32);
#pragma unroll
      for (int be = 15; be >= 12; be--) {
        const int de = 8 * be - s;
        float(&a)[4] = (be >= 14 && !(i & 1)) ? acc[be - 4] : acc[be];
        if (de >= 0 && be >= 14 && i == 2 * (15 - be)) mma0(a[0], a[1], a[2], a[3], q[0], q[1], q[2], q[3], F[2 * de + 1], F[2 * de]);
        else if (de >= 0) mma(a[0], a[1], a[2], a[3], q[0], q[1], q[2], q[3], F[2 * de + 1], F[2 * de]);
      }
    }
#pragma unroll
    for (int i = 0; i < 8; i++) acc[14 + (i >> 2)][i & 3] += acc[10 + (i >> 2)][i & 3];
    F[64] = lds32(fa + 32 * 64); F[65] = lds32(fa + 32 * 65);
#pragma unroll
    for (int i = 0; i < 6; i++) ldsm4(qd[i], qa + 128 * 11 - 16 * i);
    uint2 sv = lds64(st + 256 * 11);
    float ci[4] = {bf_lo(sv.x), bf_hi(sv.x), bf_lo(sv.y), bf_hi(sv.y)};
    float T[5][4];
#pragma unroll
    for (int i = 0; i < 16; i++) T[i >> 2][i & 3] = acc[12 + (i >> 2)][i & 3];
    nb_sync(NB_YZ, 160);
    TS(46);
    uint32_t held[2];
#pragma unroll
    for (int be = 11; be >= 0; be--) {
      if (be & 1) SPLITN(be);
      const uint32_t qp = qa + 128 * be;
#pragma unroll
      for (int k = 4; k >= 1; k--) mmac(T[k], qd[0][0], qd[0][1], qd[0][2], qd[0][3], F[16 * k + 1], F[16 * k], T[k - 1]);
      if (be >= 4) mmac(T[0], qd[0][0], qd[0][1], qd[0][2], qd[0][3], F[1], F[0], ci);
      else mma0(T[0][0], T[0][1], T[0][2], T[0][3], qd[0][0], qd[0][1], qd[0][2], qd[0][3], F[1], F[0]);
      ldsm4(qd[6], qp - 16 * 6);
      ldsm4(qd[7], qp - 16 * 7);
      if (be > 4) sv = lds64(st + 256 * (be - 1));
#pragma unroll
      for (int i = 1; i < 8; i++) {
#pragma unroll
        for (int k = 3; k >= 0; k--)
          mma(T[k][0], T[k][1], T[k][2], T[k][3], qd[i][0], qd[i][1], qd[i][2], qd[i][3], F[16 * k + 2 * i + 1], F[16 * k + 2 * i]);
        if (i < 7 && be > 0) ldsm4(qd[i - 1], qp - 128 - 16 * (i - 1));
        if (i == 2) {
          const uint32_t w0 = pack_bf(T[4][0], T[4][1]), w1 = pack_bf(T[4][2], T[4][3]);
          if (be & 1) { held[0] = w0; held[1] = w1; }
          else st_x(ydst + (be + 4) * 16, nz(w0), w1, held[0], held[1]);
          if ((be & 3) == 3 && be < 11) nb_arrive(NB_Y + 2 + (be >> 2), 160);
        }
        if (i == 4 && be > 4) { ci[0] = bf_lo(sv.x); ci[1] = bf_hi(sv.x); ci[2] = bf_lo(sv.y); ci[3] = bf_hi(sv.y); }
      }
    }
    if ((fu(T[0][0]) & fu(T[1][0]) & fu(T[2][0]) & fu(T[3][0])) == 0xffffffffu) sts32(st, 0);
    nb_arrive(NB_BDONE, 288);
    nb_arrive(NB_Y + 1, 160);
#pragma unroll
    for (int B = 1; B >= 0; B--)
      st_x(ydst + B * 32, nz(pack_bf(T[2 * B][0], T[2 * B][1])), pack_bf(T[2 * B][2], T[2 * B][3]),
           pack_bf(T[2 * B + 1][0], T[2 * B + 1][1]), pack_bf(T[2 * B + 1][2], T[2 * B + 1][3]));
  }
}

__device__ __forceinline__ void dual_exp(const uint32_t* w, uint32_t* e) {
  const float L = 1.44268798828125f;
  uint32_t mx = bmax2(bmax2(w[0], w[1]), bmax2(w[2], w[3]));
  uint32_t mn = bmin2(bmin2(w[0], w[1]), bmin2(w[2], w[3]));
  mx = bmax2(mx, __shfl_xor_sync(0xffffffffu, mx, 1));
  mn = bmin2(mn, __shfl_xor_sync(0xffffffffu, mn, 1));
  mx = bmax2(mx, __shfl_xor_sync(0xffffffffu, mx, 2));
  mn = bmin2(mn, __shfl_xor_sync(0xffffffffu, mn, 2));
  const float mx0 = bf_lo(mx) * -L, mx1 = bf_hi(mx) * -L, mn0 = bf_lo(mn) * L, mn1 = bf_hi(mn) * L;
#pragma unroll
  for (int i = 0; i < 2; i++) {
    const float a0 = bf_lo(w[2 * i]), a1 = bf_hi(w[2 * i]), b0 = bf_lo(w[2 * i + 1]), b1 = bf_hi(w[2 * i + 1]);
    e[2 * i] = pack_bf(ex2(fmaf(a0, L, mx0)), ex2(fmaf(b0, L, mx0)));
    e[2 * i + 1] = pack_bf(ex2(fmaf(a1, L, mx1)), ex2(fmaf(b1, L, mx1)));
    e[4 + 2 * i] = pack_bf(ex2(fmaf(a0, -L, mn0)), ex2(fmaf(b0, -L, mn0)));
    e[5 + 2 * i] = pack_bf(ex2(fmaf(a1, -L, mn1)), ex2(fmaf(b1, -L, mn1)));
  }
}
__device__ __forceinline__ void normalise(uint32_t* e, const float (&s)[4]) {
  const uint32_t r = pack_bf(rcp(s[0]), rcp(s[2]));
  const __nv_bfloat162 rr = *(const __nv_bfloat162*)&r;
#pragma unroll
  for (int i = 0; i < 4; i++) {
    const __nv_bfloat162 v = __hmul2(*(const __nv_bfloat162*)&e[i], (i & 1) ? __high2bfloat162(rr) : __low2bfloat162(rr));
    e[i] = *(const uint32_t*)&v;
  }
}
__host__ __device__ constexpr uint64_t qdesc(uint32_t addr) { return mkdesc(addr, 128, 256, 0); }

__global__ void __launch_bounds__(NTHREADS, 1)
fused_kernel(const Params P, const __grid_constant__ CUtensorMap mx, const __grid_constant__ CUtensorMap mw,
             const __grid_constant__ CUtensorMap mo, const __grid_constant__ CUtensorMap mu,
             const __grid_constant__ CUtensorMap mout) {
  constexpr uint32_t sb = SB;
  const int tid = threadIdx.x, lane = tid & 31;
  const int warp = __shfl_sync(0xffffffffu, tid >> 5, 0);
  const int b = blockIdx.x, oct = b >> 3, i8 = b & 7;
  const int rt = (((oct & 4) ? ~oct : oct) & 3) * 2 + (i8 >> 2);
  const int hp = (oct >> 2) * 4 + (i8 & 3);

  const int wg = warp >> 2, w = warp & 3;
  const int d = b * 4 + ((tid >> 5) & 3);
  const KgenRaw raw = kgen_load(P, d, (tid >> 7) & 1, lane, (tid + 128) & 256);
  const uint32_t tb = sb + OFF_T + w * T_CH;
  if (warp >= 12) asm volatile("setmaxnreg.dec.sync.aligned.u32 32;");
  if (warp == 14) {
    asm volatile("prefetch.tensormap [%0];" ::"l"(&mw) : "memory");
    asm volatile("prefetch.tensormap [%0];" ::"l"(&mx) : "memory");
    asm volatile("prefetch.tensormap [%0];" ::"l"(&mu) : "memory");
  }
  if (warp == 12) {
    if (lane == 0) {
#pragma unroll
      for (int i = 0; i < 9; i++) mbar_init(BAR(i), 1);
      asm volatile("fence.mbarrier_init.release.cluster;" ::: "memory");
    }
    __syncwarp();
    if (lane < 9) mbar_expect(BAR(0) + 8 * lane, lane == 0 ? 16384 : 28672);
    __syncwarp();
    nb_arrive(NB_PROD, 384);
#pragma unroll 1
    for (int kb = 0; kb < 8; kb++) {
      if (kb == U_AT) e_tma4d(sb + OFF_STG0, &mu, BAR(MB_URAW), i8 * 64, oct * 2);
      e_tma3d(sb + OFF_W + kb * 12288, &mw, BAR(MB_FULL) + 8 * kb, hp * 32, kb * 64, 0);
      if (kb < 5) e_tma2d(sb + OFF_X + (kb < 2 ? kb + 3 : kb - 2) * 16384, &mx, BAR(MB_FULL) + 8 * kb, kb * 64, rt * 256);
    }
    if (smem_u32(smem_raw) != SB) __trap();
    if (lane == 0) TS1(54);
  }
  if (warp >= 12) {
    if (warp == 12) {
      nb_sync(NB_GATE + 1, 64);
      uint32_t slot = sb + OFF_X + 3 * 16384;
#pragma unroll 1
      for (int n = 0; n < 11; n++) {
        mbar_spin(BAR(MB_EMPTY) + 8 * n);
        const int m = n + 5;
        e_tma2d(slot, &mx, BAR(MB_FULL) + 8 * m, (m & 7) * 64, rt * 256 + (m >> 3) * 128);
        slot = slot == sb + OFF_X + 4 * 16384 ? sb + OFF_X : slot + 16384;
        if (n == 0) e_prefetch(P.x + (size_t)(rt * 256 + 128 + hp * 8) * 512, 8192);
        if (n == 7) {
          e_prefetch(P.wo + (size_t)b * 2048, 4096);
          asm volatile("prefetch.tensormap [%0];" ::"l"(&mo) : "memory");
          asm volatile("prefetch.tensormap [%0];" ::"l"(&mout) : "memory");
        }
      }
#pragma unroll 1
      for (int i = 0; i < 8; i++) {
        mbar_wait(BAR(MB_EMPTY + 10) + 8 * ((0x54332222u >> (4 * i)) & 7));
        const int w0 = (0x54736210u >> (4 * i)) & 7;
        e_tma3d(sb + OFF_W + w0 * 16384, &mo, BAR(MB_WO), 0, w0 * 64, (hp & 3) * 2);
      }
    } else {
      if (warp == 13) {
        if (lane == 0) {
#pragma unroll
          for (int i = 9; i < 40; i++) mbar_init(BAR(i), i < MB_EMPTY ? 1 : 4);
          asm volatile("fence.mbarrier_init.release.cluster;" ::: "memory");
        }
        __syncwarp();
        if (lane < 14 && lane != 9) mbar_expect(BAR(MB_FULL + 8) + 8 * lane, lane == 8 ? 131072 : (lane == 10 ? 8192 : (lane == 13 ? 24576 : 16384)));
        nb_arrive(NB_GATE + 1, 64);
      } else if (warp == 14) {
        e_prefetch(P.x + (size_t)(rt * 256 + hp * 8) * 512, 8192);
      }
      nb_sync(NB_PROD, 384);
      if (warp == 15) {
        const uint4 v0 = __ldg((const uint4*)P.wphi + hp * 64 + lane), v1 = __ldg((const uint4*)P.wphi + hp * 64 + 32 + lane);
        sts128(sb + OFF_PHI + (lane & 1) * 256 + (lane >> 1) * 16, v0.x, v0.y, v0.z, v0.w);
        sts128(sb + OFF_PHI + 512 + (lane & 1) * 256 + (lane >> 1) * 16, v1.x, v1.y, v1.z, v1.w);
        const uint32_t one = (((lane >> 3) ^ (lane >> 4)) & 1) ? 0u : ((lane & 1) ? 0x3F800000u : 0x3F80u);
        const int q = (lane >> 1) & 3;
        sts128(sb + OFF_EYE + lane * 16, q == 0 ? one : 0u, q == 1 ? one : 0u, q == 2 ? one : 0u, q == 3 ? one : 0u);
        sts64(sb + OFF_ONE + lane * 8, 0x3F803F80u, 0x3F803F80u);
        asm volatile("fence.proxy.async.shared::cta;" ::: "memory");
        nb_arrive(NB_KREAD, 160);
      }
      uint32_t* cnt = (uint32_t*)(P.xs + X_CNT) + (warp == 13 ? i8 : (warp == 14 ? 8 + rt : 16 + oct)) * 32;
      const unsigned target = (ld_x32(cnt) & ~15u) + 16;
      if (warp != 14) {
        if (warp == 15) mbar_wait(BAR(MB_EMPTY + ZERO_STEP));
        uint4* pz = P.xs + (warp == 13 ? X_PART + (hp * 8 + rt) * 144 : X_Y + b * 1024) + lane;
#pragma unroll 1
        for (int i = (warp == 13 ? 144 : 1024) - lane; i > 0; i -= 32, pz += 32) st_x(pz, 0, 0, 0, 0);
      }
      if (warp == 15) __syncwarp();
      else nb_sync(warp == 13 ? NB_INIT : NB_ODONE, warp == 13 ? 160 : 288);
      if (lane == 0) asm volatile("red.release.gpu.global.add.u32 [%0], %1;" ::"l"(cnt), "r"(warp == 15 ? 2 : 1) : "memory");
      if (lane == 0) TS1(warp == 13 ? 50 : (warp == 14 ? 57 : 53));
      __syncwarp();
      if (warp == 14) nb_arrive(NB_GATE + 1, 160);
      asm volatile("fence.proxy.async.shared::cta;" ::: "memory");
      if (warp == 13) cnt += ((lane & 1 ? b >> 4 : i8 ^ (lane & 4)) - i8) * 32;
#pragma unroll 1
      for (int i = 0; i < SPIN_MAX; i++) {
        unsigned v;
        asm volatile("ld.acquire.gpu.global.u32 %0, [%1];" : "=r"(v) : "l"(cnt) : "memory");
        if (__all_sync(0xffffffffu, (int)(v - target) >= 0)) break;
      }
      if (lane == 0) TS1(warp == 13 ? 51 : (warp == 14 ? 58 : 55));
      if (warp == 15) { nb_arrive(NB_YZ, 160); return; }
      asm volatile("fence.proxy.async.global;" ::: "memory");
      if (warp == 13) {
        mbar_wait(BAR(MB_EMPTY + 11));
        e_expect(BAR(MB_UFULL), 4 * U_CH);
        e_bulk(sb + OFF_U, P.xs + X_UT + b * (U_CH / 4), 4 * U_CH, BAR(MB_UFULL));
      } else {
        const uint4* src = P.xs + X_O + (rt * 4 + (hp >> 2)) * 4096;
        e_bulk(sb + OFF_X + 32768 + 57344, src + 3584, 8192, BAR(MB_O));
        e_bulk(sb + OFF_X + 32768, src, 16384, BAR(MB_O + 1));
        e_bulk(sb + OFF_X + 49152, src + 1024, 16384, BAR(MB_O + 2));
        e_bulk(sb + OFF_STG0, src + 3200, 6144, BAR(MB_O + 3));
        nb_sync(NB_BDONE, 288);
        asm volatile("fence.proxy.async.shared::cta;" ::: "memory");
        e_bulk(sb + OFF_U, src + 2048, 18432, BAR(MB_O + 3));
      }
    }
    return;
  }

  asm volatile("setmaxnreg.inc.sync.aligned.u32 160;");
  const int t = tid & 127;
  const int g = lane >> 2, c = lane & 3;
  const uint32_t kp = ((tb + 127) & ~127u) + (wg & 1) * 2048;
  const KgenAddr kad = kgen_addr(lane, kp);
  if (wg) nb_sync(NB_PROD, 384);
  SPLIT();
  float k[5][4], k2048, ksc;
  if (wg) {
    kgen_unit(raw, kad, blockIdx.y, k, k2048, ksc);
    TS(40 + wg);
    if ((fu(k[0][0]) & fu(k[1][0]) & fu(k[2][0]) & fu(k[3][0]) & fu(k[4][0])) == 0xffffffffu) sts32(kp, 0);
  }
  if (wg) nb_arrive(0, 384);
  if (wg) {
    if (wg == 1) {
      uint32_t h[10];
#pragma unroll
      for (int j = 0; j < 10; j++) h[j] = hu(__floats2half2_rn(k[j >> 1][2 * (j & 1)], k[j >> 1][2 * (j & 1) + 1]));
      sts128(kp + lane * 16, h[0], h[1], h[2], h[3]);
      sts128(kp + 512 + lane * 16, h[4], h[5], h[6], h[7]);
      sts128(kp + 1024 + lane * 16, h[8], h[9], fu(k2048), fu(ksc));
      nb_arrive(NB_PREP, 256);
    }
  } else {
    nb_sync(NB_KREAD, 160);
  }
  if (wg == 1) {
    mbar_wait(BAR(MB_URAW));
    TS(48);
    uint4* dst = P.xs + X_UT + (i8 * 64 + g) * (U_CH / 16) + (w & 1) * (U_ODD / 16) + U_PAD / 16 + oct * 8 + (w >> 1) * 4 + c;
    const int ln = ((lane >> 1) & 3) + 4 * (lane & 1);
    uint32_t r[8][4];
#pragma unroll
    for (int i = 0; i < 8; i++) ldsm4t(r[i], sb + OFF_STG0 + w * 4096 + ((lane >> 3) * 8 + ln) * 128 + ((i ^ ln) << 4));
#pragma unroll
    for (int i = 0; i < 8; i++) dst[i * (U_CH / 2)] = make_uint4(r[i][0], r[i][1], r[i][2], r[i][3]);
    nb_arrive(NB_INIT, 160);
    if (lane == 0) mbar_arrive(BAR(MB_AUX));
  }
  {
    if (wg == 2) {
#pragma unroll
      for (int j = 0; j < 5; j++) { k[j][0] *= ksc; k[j][1] *= ksc; k[j][2] *= ksc; k[j][3] *= ksc; }
      const unsigned short dsk = __ldg((const unsigned short*)P.Dskip + d);
      nb_sync(NB_PREP, 256);
      {
        const uint32_t src = kp + 2048 + lane * 16;
        const uint4 v0 = lds128(src), v1 = lds128(src + 512), v2 = lds128(src + 1024);
        const uint32_t h[10] = {v0.x, v0.y, v0.z, v0.w, v1.x, v1.y, v1.z, v1.w, v2.x, v2.y};
#pragma unroll
        for (int j = 0; j < 10; j++) {
          const float2 f = __half22float2(*(const __half2*)&h[j]);
          k[j >> 1][2 * (j & 1)] = fmaf(f.x, uf(v2.w), k[j >> 1][2 * (j & 1)]);
          k[j >> 1][2 * (j & 1) + 1] = fmaf(f.y, uf(v2.w), k[j >> 1][2 * (j & 1) + 1]);
        }
        k2048 += uf(v2.z);
      }
#pragma unroll
      for (int o2 = 16; o2; o2 >>= 1) k2048 += __shfl_xor_sync(0xffffffffu, k2048, o2);
      if (lane == 0) k[0][0] += bf_lo(dsk);
      __syncwarp();
      TS(34);
      build_tables(tb, lane, k, k2048);
      TS(35);
      uint4* const g_y = P.xs + X_Y;
      conv_channel(sb + OFF_U + w * U_CH, tb, lane, g_y + (size_t)d * 256 + lane);
      nb_arrive(NB_Y, 160);
      TS(37);
      if (w == 0) TSDUMP(32);
      return;
    }
    if (wg == 1) {
      mbar_wait(BAR(MB_EMPTY + 4));
      mbar_spin(BAR(MB_EMPTY + 6));
    }
    TS(wg * 16 + 1);
  }

  float acc[2][48];
  {
    uint32_t fb = BAR(MB_FULL) + 64 * wg;
    uint32_t da = (uint32_t)mkdesc(sb + OFF_X, 16, 0, 0) + (wg ? 1024 : 3072), db = (uint32_t)mkdesc(sb + OFF_W, 4096, 0, 0);
    constexpr uint64_t ha = mkdesc(0, 0, 1024, 1), hb = mkdesc(0, 0, 512, 2);
    mbar_spin(fb);
    if (wg == 0) nb_sync(0, 384);
    TS(wg * 16 + 2);
#pragma unroll 1
    for (int kb = 0; kb < 8; kb++) {
      const uint32_t ready = mbar_test(kb < 7 ? fb + 8 : fb);
      WG_FENCE();
#pragma unroll
      for (int k = 0; k < 4; k++) {
        wgmma_ss_n96(acc[0], ha | (da + 2 * k), hb | (db + 64 * k), k ? 1 : kb);
        wgmma_ss_n96(acc[1], ha | (da + 2 * k + 512), hb | (db + 64 * k), k ? 1 : kb);
      }
      WG_COMMIT();
      WG_WAIT(1);
      if (kb > 0) e_arrive(fb + 8 * (MB_EMPTY - MB_FULL - 1));
      if (!ready) mbar_spin(fb + 8);
      fb += 8; db += 768;
      da = da == (uint32_t)mkdesc(sb + OFF_X + 65536, 16, 0, 0) ? da - 4096 : da + 1024;
    }
    WG_WAIT(0);
    e_arrive(fb + 8 * (MB_EMPTY - MB_FULL - 1));
    SPLIT();
  }
  TS(wg * 16 + 3);

  constexpr uint32_t stg0 = sb + OFF_STG0, stg1 = sb + OFF_X + 32768;
  uint4* const g_part = P.xs + X_PART;
  uint4* const g_o = P.xs + X_O;
  constexpr uint32_t kvs = stg0;
  auto pack8 = [](const float* a) { return make_uint4(pack_bf(a[0], a[1]), pack_bf(a[2], a[3]), pack_bf(a[4], a[5]), pack_bf(a[6], a[7])); };
  auto stage_k = [&](auto nt, const uint4* af, const uint4* vp, uint32_t sl, uint32_t free_bar) {
    constexpr int NU = 2 * decltype(nt)::value;
    float p[NU][8], rs[2 * NU][4];
    uint32_t ek[8 * NU];
    WG_FENCE();
#pragma unroll
    for (int u = 0; u < NU; u++) wgmma_rs_n16(p[u], af[u], qdesc(sb + OFF_PHI + (u & 1) * 512), 0);
    WG_COMMIT();
    WG_WAIT(0);
#pragma unroll
    for (int u = 0; u < NU; u++) {
      const uint32_t pw[4] = {pack_bf(p[u][0], p[u][2]), pack_bf(p[u][1], p[u][3]), pack_bf(p[u][4], p[u][6]), pack_bf(p[u][5], p[u][7])};
      dual_exp(pw, ek + 8 * u);
    }
    TS(wg * 16 + 12);
    mbar_spin(free_bar);
    WG_FENCE();
#pragma unroll
    for (int i = 0; i < 2 * NU; i++) wgmma_rs_n8(rs[i], make_uint4(ek[4 * i], ek[4 * i + 1], ek[4 * i + 2], ek[4 * i + 3]), qdesc(sb + OFF_ONE), 0);
    WG_COMMIT();
#pragma unroll
    for (int i = 0; i < NU; i++) stsm4(sl + (i >> 1) * 4 * SLAB + 2048 + (i & 1) * 512, vp[i].x, vp[i].y, vp[i].z, vp[i].w);
    if (NU == 4 || lane < 16) sts128(sl + (lane >> 4) * (4 * SLAB - 256) + 3072, 0x3F803F80u, 0x3F803F80u, 0x3F803F80u, 0x3F803F80u);
    WG_WAIT(0);
#pragma unroll
    for (int i = 0; i < 2 * NU; i++) {
      normalise(ek + 4 * i, rs[i]);
      stsm4(sl + (i >> 2) * 4 * SLAB + (i & 3) * 512, ek[4 * i], ek[4 * i + 1], ek[4 * i + 2], ek[4 * i + 3]);
    }
    asm volatile("fence.proxy.async.shared::cta;" ::: "memory");
  };
  auto contract = [&](float (&kc)[20], uint32_t stg, int acc_in) {
    WG_FENCE();
#pragma unroll
    for (int s = 0; s < 8; s++) wgmma_ss_n40(kc, qdesc(stg + s * SLAB), qdesc(stg + s * SLAB + 2048), s ? 1 : acc_in);
    WG_COMMIT();
    WG_WAIT(0);
  };
  uint32_t eq[32];
  {
    uint4 af[4], aq[4], vp[4];
    float kc[20];
#pragma unroll
    for (int u = 0; u < 4; u++) { af[u] = pack8(acc[u >> 1] + 16 + 8 * (u & 1)); vp[u] = pack8(acc[u >> 1] + 32 + 8 * (u & 1)); }
    const uint32_t hand = stg1 + 16384 + 8192 + w * 2048 + lane * 16;
    if (wg) {
      sts128(hand, af[2].x, af[2].y, af[2].z, af[2].w); sts128(hand + 512, af[3].x, af[3].y, af[3].z, af[3].w);
      sts128(hand + 1024, vp[2].x, vp[2].y, vp[2].z, vp[2].w); sts128(hand + 1536, vp[3].x, vp[3].y, vp[3].z, vp[3].w);
      nb_arrive(NB_HAND, 256);
    }
#pragma unroll
    for (int u = 0; u < 4; u++) aq[u] = pack8(acc[u >> 1] + 8 * (u & 1));
    if (wg == 0) {
      stage_k(std::integral_constant<int, 2>(), af, vp, stg0 + w * SLAB + lane * 16, BAR(MB_AUX));
      TS(13);
      nb_sync(NB_WG0, 128);
      contract(kc, stg0, 0);
      mbar_wait(BAR(MB_UFULL));
      TS(15);
      nb_sync(NB_HAND, 256);
      af[0] = lds128(hand); af[1] = lds128(hand + 512); vp[0] = lds128(hand + 1024); vp[1] = lds128(hand + 1536);
      nb_sync(NB_WG0, 128);
    }
    stage_k(std::integral_constant<int, 1>(), af, vp, stg1 + (wg ? w : 4 + w) * SLAB + lane * 16, BAR(MB_EMPTY + 15));
    TS(wg * 16 + 14);
    float p[4][8];
    if (wg) {
      nb_arrive(NB_ST0, 256);
      nb_arrive(NB_GATE, 256);
    } else {
      uint4* pp = g_part + (size_t)(hp * 8 + rt) * 144 + t;
      uint32_t* pz = (uint32_t*)(pp - t + 128) + w * 16 + c * 8 + g;
      asm volatile("" : "+l"(pp), "+l"(pz));
      nb_sync(NB_ST0, 256);
      contract(kc, stg1, 1);
      TS(6);
      float kv[8];
#pragma unroll
      for (int i = 0; i < 8; i++) kv[i] = w & 2 ? kc[8 + i] : kc[i];
      st_x(pp, nz(pack_bf(kv[0], kv[1])), pack_bf(kv[2], kv[3]), pack_bf(kv[4], kv[5]), pack_bf(kv[6], kv[7]));
      if (c < 2) st_x32(pz, nz(fu(c ? kc[18] : kc[16])));
      TS(5);
    }
    SPLIT();
    WG_FENCE();
#pragma unroll
    for (int u = 0; u < 4; u++) wgmma_rs_n16(p[u], aq[u], qdesc(sb + OFF_PHI + (u & 1) * 512), 0);
    WG_COMMIT();
    WG_WAIT(0);
#pragma unroll
    for (int u = 0; u < 4; u++) {
      const uint32_t pw[4] = {pack_bf(p[u][0], p[u][2]), pack_bf(p[u][1], p[u][3]), pack_bf(p[u][4], p[u][6]), pack_bf(p[u][5], p[u][7])};
      dual_exp(pw, eq + 8 * u);
    }
    SPLIT();
  }
  TS(wg * 16 + 4);
  if (wg == 1) {
    mbar_wait(BAR(MB_UFULL));
    const uint4* ps = g_part + (size_t)hp * 8 * 144 + t;
    const uint32_t* zs = (const uint32_t*)(g_part + (size_t)(hp * 8 + (lane >> 4) * 4) * 144 + 128) + w * 16 + (lane & 15);
    uint4 v[8];
    uint32_t zv[4];
#pragma unroll 1
    for (int it = 0; it < SPIN_MAX; it++) {
#pragma unroll
      for (int i = 0; i < 8; i++) v[i] = ld_x(ps + i * 144);
#pragma unroll
      for (int i = 0; i < 4; i++) zv[i] = ld_x32(zs + i * 576);
      uint32_t m = min(min(zv[0], zv[1]), min(zv[2], zv[3]));
#pragma unroll
      for (int i = 0; i < 8; i++) m = min(m, v[i].x);
      if (__all_sync(0xffffffffu, m != 0)) break;
    }
    float s[8];
    WG_FENCE();
#pragma unroll
    for (int r = 0; r < 8; r++) wgmma_rs_n16(s, v[r], qdesc(sb + OFF_EYE), r);
    WG_COMMIT();
    float zsum = (uf(zv[0]) + uf(zv[1])) + (uf(zv[2]) + uf(zv[3]));
    zsum += __shfl_xor_sync(0xffffffffu, zsum, 16);
    const uint32_t z1 = pack_bf(zsum, 1.f);
    if (lane < 16) sts128(kvs + w * 768 + 512 + lane * 16, z1, z1, z1, z1);
    WG_WAIT(0);
    stsm4(kvs + w * 768 + lane * 16, pack_bf(s[0], s[1]), pack_bf(s[2], s[3]), pack_bf(s[4], s[5]), pack_bf(s[6], s[7]));
    asm volatile("fence.proxy.async.shared::cta;" ::: "memory");
    TS(22);
  }
  nb_sync(NB_KV, 256);
  {
    float n[8][12];
    WG_FENCE();
#pragma unroll
    for (int i = 0; i < 8; i++) wgmma_rs_n24(n[i], make_uint4(eq[4 * i], eq[4 * i + 1], eq[4 * i + 2], eq[4 * i + 3]), qdesc(kvs + (i & 3) * 768), 0);
    WG_COMMIT();
    uint32_t* od = (uint32_t*)(g_o + (size_t)((rt * 4 + wg * 2) * 32 + hp * 2) * 128) + w * 64 + lane;
    WG_WAIT(0);
#pragma unroll
    for (int u = 0; u < 4; u++) {
      float(&np)[12] = n[2 * u];
      const float(&nm)[12] = n[2 * u + 1];
      const float q0 = np[9] * rcp(nm[9]), q1 = np[11] * rcp(nm[11]);
      const float r0 = rcp(fmaf(nm[8], q0, fmaf(np[9], 1e-6f, np[8]))), r1 = rcp(fmaf(nm[10], q1, fmaf(np[11], 1e-6f, np[10])));
#pragma unroll
      for (int i = 0; i < 8; i++) np[i] = fmaf(nm[i], (i & 2) ? q1 : q0, np[i]);
      uint32_t* o = od + (u >> 1) * 16384 + (u & 1) * 512;
      o[0] = pack_bf(np[0] * r0, np[1] * r0);
      o[32] = pack_bf(np[2] * r1, np[3] * r1);
      o[256] = pack_bf(np[4] * r0, np[5] * r0);
      o[288] = pack_bf(np[6] * r1, np[7] * r1);
      if (u == 1) SPLIT();
    }
  }
  TS(wg * 16 + 7);
  nb_arrive(NB_ODONE, 288);
  if (wg) {
    const uint4* src = P.xs + X_Y + (oct * 32 + c * 8) * 256 + (2 * w + (g >> 2)) * 32 + i8 * 4 + (g & 3);
    __nv_bfloat16* dst = P.out + (size_t)((2 * w + (g >> 2)) * 256 + i8 * 16 + (g & 3) * 2) * 1024 + 512 + oct * 32 + c * 8;
    nb_sync(NB_GATE + 1, 160);
    nb_sync(NB_Y + w, 160);
    uint4 v[8];
#pragma unroll 1
    for (int it = 0; it < SPIN_MAX; it++) {
      uint32_t m = 0xffffffffu;
#pragma unroll
      for (int i = 0; i < 8; i++) v[i] = ld_x(src + i * 256);
#pragma unroll
      for (int i = 0; i < 8; i++) m = min(m, v[i].x);
      if (__all_sync(0xffffffffu, m != 0)) break;
    }
#pragma unroll
    for (int i = 0; i < 8; i++) *(uint4*)(dst + (size_t)((i >> 2) * 128 + ((i >> 1) & 1) * 8 + (i & 1)) * 1024) = tr_row(v, i);
    TS(31);
    GT(63);
    if (w == 0) TSDUMP(16);
    return;
  }
  mbar_wait(BAR(MB_WO));
  nb_sync(NB_BDONE, 288);
  TS(8);
  mbar_spin(BAR(MB_O));
  TS(9);
  constexpr uint64_t ha = mkdesc(0, 0, 128, 0), hb = mkdesc(0, 0, 1024, 1);
  constexpr uint32_t da0 = (uint32_t)mkdesc(stg1, 1024, 0, 0), db0 = (uint32_t)mkdesc(sb + OFF_W, 8192, 0, 0);
  const uint32_t ot = ((sb + OFF_T + 1023) & ~1023u) + w * 4096;
  auto store_half = [&](const float* oc, int hf) {
#pragma unroll
    for (int i = 0; i < 8; i += 2)
      stsm4(ot + hf * 2048 + (lane & 15) * 128 + (((i + (lane >> 4)) ^ lane) & 7) * 16, pack_bf(oc[4 * i], oc[4 * i + 1]),
            pack_bf(oc[4 * i + 2], oc[4 * i + 3]), pack_bf(oc[4 * i + 4], oc[4 * i + 5]), pack_bf(oc[4 * i + 6], oc[4 * i + 7]));
    asm volatile("fence.proxy.async.shared::cta;" ::: "memory");
    __syncwarp();
    e_store2d(&mout, ot + hf * 2048, (hp & 3) * 128 + hf * 64, (rt * 4 + (hp >> 2)) * 64 + w * 16);
  };
  float oc[64];
#pragma unroll 1
  for (int j = 0; j < 8; j++) {
    const int kb = (j + 7) & 7;
    if ((j & 1) && j < 6) mbar_spin(BAR(MB_O + 1) + 4 * (j - 1));
    WG_FENCE();
#pragma unroll
    for (int k = 0; k < 4; k++) wgmma_ss_n128(oc, ha | (da0 + 512 * kb + 128 * k), hb | (db0 + 1024 * kb + 128 * k), k ? 1 : j);
    WG_COMMIT();
  }
  WG_WAIT(0);
  TS(10);
  store_half(oc, 0);
  store_half(oc + 32, 1);
  asm volatile(ELECT "cp.async.bulk.commit_group;\n@p cp.async.bulk.wait_group.read 0;\n}\n" ::: "memory");
  TS(wg * 16 + 11);
  GT(61 + wg);
  if (w == 0) TSDUMP(0);
  if (w == 1) TSDUMP(48);
}

typedef CUresult (*EncodeFn)(CUtensorMap*, CUtensorMapDataType, cuuint32_t, void*, const cuuint64_t*, const cuuint64_t*,
                             const cuuint32_t*, const cuuint32_t*, CUtensorMapInterleave, CUtensorMapSwizzle,
                             CUtensorMapL2promotion, CUtensorMapFloatOOBfill);

}

extern "C" void kernel_launch(void* const* d_in, const int* in_sizes, int n_in, void* d_out, int out_size) {
  (void)in_sizes; (void)n_in; (void)out_size;
  void* fn = nullptr;
  cudaDriverEntryPointQueryResult qr;
  cudaGetDriverEntryPoint("cuTensorMapEncodeTiled", &fn, cudaEnableDefault, &qr);
  EncodeFn enc = (EncodeFn)fn;
  CUtensorMap mx, mw, mo, mu, mout;
  const cuuint32_t es[5] = {1, 1, 1, 1, 1};
  {
    cuuint64_t dims[2] = {512, 2048}, st[1] = {1024};
    cuuint32_t box[2] = {64, 128};
    enc(&mx, CU_TENSOR_MAP_DATA_TYPE_BFLOAT16, 2, d_in[0], dims, st, box, es, CU_TENSOR_MAP_INTERLEAVE_NONE,
        CU_TENSOR_MAP_SWIZZLE_128B, CU_TENSOR_MAP_L2_PROMOTION_L2_128B, CU_TENSOR_MAP_FLOAT_OOB_FILL_NONE);
  }
  {
    cuuint64_t dims[3] = {512, 512, 3}, st[2] = {3072, 1024};
    cuuint32_t box[3] = {32, 64, 3};
    enc(&mw, CU_TENSOR_MAP_DATA_TYPE_BFLOAT16, 3, d_in[1], dims, st, box, es, CU_TENSOR_MAP_INTERLEAVE_NONE,
        CU_TENSOR_MAP_SWIZZLE_64B, CU_TENSOR_MAP_L2_PROMOTION_L2_128B, CU_TENSOR_MAP_FLOAT_OOB_FILL_NONE);
  }
  {
    cuuint64_t dims[3] = {64, 512, 8}, st[2] = {1024, 128};
    cuuint32_t box[3] = {64, 64, 2};
    enc(&mo, CU_TENSOR_MAP_DATA_TYPE_BFLOAT16, 3, d_in[3], dims, st, box, es, CU_TENSOR_MAP_INTERLEAVE_NONE,
        CU_TENSOR_MAP_SWIZZLE_128B, CU_TENSOR_MAP_L2_PROMOTION_L2_128B, CU_TENSOR_MAP_FLOAT_OOB_FILL_NONE);
  }
  {
    cuuint64_t dims[4] = {512, 4, 16, 32}, st[3] = {16384, 1024, 65536};
    cuuint32_t box[4] = {64, 4, 16, 2};
    enc(&mu, CU_TENSOR_MAP_DATA_TYPE_BFLOAT16, 4, d_in[4], dims, st, box, es, CU_TENSOR_MAP_INTERLEAVE_NONE,
        CU_TENSOR_MAP_SWIZZLE_128B, CU_TENSOR_MAP_L2_PROMOTION_L2_128B, CU_TENSOR_MAP_FLOAT_OOB_FILL_NONE);
  }
  {
    cuuint64_t dims[2] = {1024, 2048}, st[1] = {2048};
    cuuint32_t box[2] = {64, 16};
    enc(&mout, CU_TENSOR_MAP_DATA_TYPE_BFLOAT16, 2, d_out, dims, st, box, es, CU_TENSOR_MAP_INTERLEAVE_NONE,
        CU_TENSOR_MAP_SWIZZLE_128B, CU_TENSOR_MAP_L2_PROMOTION_NONE, CU_TENSOR_MAP_FLOAT_OOB_FILL_NONE);
  }
  Params P;
  P.x = (const __nv_bfloat16*)d_in[0];
  P.wphi = (const __nv_bfloat16*)d_in[2];
  P.wo = (const __nv_bfloat16*)d_in[3];
  P.logA = (const __nv_bfloat16*)d_in[5];
  P.Aim = (const __nv_bfloat16*)d_in[6];
  P.Cre = (const __nv_bfloat16*)d_in[7];
  P.Cim = (const __nv_bfloat16*)d_in[8];
  P.logdt = (const __nv_bfloat16*)d_in[9];
  P.Dskip = (const __nv_bfloat16*)d_in[10];
  P.out = (__nv_bfloat16*)d_out;
  cudaGetSymbolAddress((void**)&P.xs, g_x);
  P.ts = nullptr;
  cudaFuncSetAttribute(fused_kernel, cudaFuncAttributeMaxDynamicSharedMemorySize, SMEM_BYTES);
  fused_kernel<<<NCTA, NTHREADS, SMEM_BYTES>>>(P, mx, mw, mo, mu, mout);
}
```

```cpp
#include <cuda_runtime.h>
#include <cuda_bf16.h>
#include <cuda_fp16.h>
#include <cuda.h>
#include <stdint.h>
#include <type_traits>

#define DBG_TS 0

namespace {

constexpr int NTHREADS = 512;
constexpr int NCTA = 128;
constexpr int OFF_W = 0;
constexpr int OFF_X = 98304;
constexpr int OFF_U = OFF_X + 65536;
constexpr int U_CH = 4416, U_ODD = 2240, U_PAD = 128;
constexpr int OFF_STG0 = OFF_U + 18432;
constexpr int SLAB = 3328;
constexpr int OFF_T = OFF_STG0 + 8 * SLAB;
constexpr int T_CH = 5216;
constexpr int T_D = 0;
constexpr int T_5 = 2144;
constexpr int T_3 = T_5 + 384;
constexpr int T_7 = T_5 + 1024;
constexpr int T_9 = T_7 + 320;
constexpr int T_KC = T_9 + 320;
constexpr int T_ST = T_5 - 2048;
constexpr int OFF_PHI = OFF_T + 4 * T_CH;
constexpr int OFF_EYE = OFF_PHI + 1024, OFF_ONE = OFF_EYE + 512;
constexpr int OFF_BAR = OFF_ONE + 256;
constexpr int SMEM_BYTES = OFF_BAR + 512 + 256 * DBG_TS;
constexpr uint32_t SB = 1024;
static_assert(T_KC + 2 * 656 <= T_CH, "table size");
static_assert(SMEM_BYTES <= 232448, "smem");
constexpr int MB_URAW = 0, MB_FULL = 1  , MB_WO = 17, MB_UFULL = 18, MB_O = 19  ,
              MB_EMPTY = 23  , MB_AUX = 39;
__host__ __device__ constexpr uint32_t BAR(int i) { return SB + OFF_BAR + 8 * i; }
constexpr int NB_WG0 = 1, NB_ODONE = 2, NB_ST0 = 3, NB_HAND = 4, NB_KV = 5, NB_YZ = 6, NB_INIT = 7, NB_PREP = 8, NB_PROD = 9, NB_KREAD = 10,
              NB_BDONE = 11, NB_GATE = 12  , NB_Y = 7  ;
constexpr int U_AT = 2;
constexpr int ZERO_STEP = 12;
constexpr int SPIN_MAX = 1 << 16;

constexpr int X_CNT = 0;
constexpr int X_PART = 256;
constexpr int X_O = X_PART + 16 * 8 * 144;
constexpr int X_Y = X_O + 32 * 32 * 128;
constexpr int X_UT = X_Y + 512 * 8 * 32;
constexpr int X_SIZE = X_UT + 512 * (U_CH / 16);
__device__ __align__(128) uint4 g_x[X_SIZE];
extern __shared__ uint8_t smem_raw[];
#define TS(i) do {} while (0)
#define TS1(i) do {} while (0)
#define GT(i) do {} while (0)
#define TSDUMP(base) do {} while (0)

__device__ __forceinline__ uint32_t smem_u32(const void* p) { return (uint32_t)__cvta_generic_to_shared(p); }
__device__ __forceinline__ void mbar_arrive(uint32_t b) {
  asm volatile("mbarrier.arrive.shared::cta.b64 _, [%0];" ::"r"(b) : "memory");
}
__device__ __forceinline__ void mbar_wait(uint32_t b) {
  uint32_t done = 0;
#pragma unroll 1
  for (int i = 0; i < SPIN_MAX && !done; i++) {
    asm volatile("{\n.reg .pred p;\nmbarrier.try_wait.parity.shared::cta.b64 p, [%1], 0, 4000;\nselp.u32 %0, 1, 0, p;\n}\n"
                 : "=r"(done) : "r"(b) : "memory");
  }
}
__device__ __forceinline__ void mbar_spin(uint32_t b) {
  uint32_t done = 0;
#pragma unroll 1
  for (int i = 0; i < (SPIN_MAX << 4) && !done; i++) {
    asm volatile("{\n.reg .pred p;\nmbarrier.try_wait.parity.shared::cta.b64 p, [%1], 0;\nselp.u32 %0, 1, 0, p;\n}\n"
                 : "=r"(done) : "r"(b) : "memory");
  }
}
__device__ __forceinline__ uint32_t mbar_test(uint32_t b) {
  uint32_t done;
  asm volatile("{\n.reg .pred p;\nmbarrier.test_wait.parity.shared::cta.b64 p, [%1], 0;\nselp.u32 %0, 1, 0, p;\n}\n" : "=r"(done) : "r"(b) : "memory");
  return done;
}
__device__ __forceinline__ void mbar_init(uint32_t b, int n) {
  asm volatile("mbarrier.init.shared::cta.b64 [%0], %1;" ::"r"(b), "r"(n) : "memory");
}
__device__ __forceinline__ void mbar_expect(uint32_t b, int bytes) {
  asm volatile("mbarrier.arrive.expect_tx.shared::cta.b64 _, [%0], %1;" ::"r"(b), "r"(bytes) : "memory");
}
__device__ __forceinline__ void nb_sync(int id, int n) { asm volatile("bar.sync %0, %1;" ::"r"(id), "r"(n) : "memory"); }
__device__ __forceinline__ void nb_arrive(int id, int n) { asm volatile("bar.arrive %0, %1;" ::"r"(id), "r"(n) : "memory"); }
#define ELECT "{\n.reg .pred p;\nelect.sync _|p, 0xffffffff;\n@p "
__device__ __forceinline__ void e_arrive(uint32_t b) {
  asm volatile(ELECT "mbarrier.arrive.shared::cta.b64 _, [%0];\n}\n" ::"r"(b) : "memory");
}
__device__ __forceinline__ void e_expect(uint32_t b, int bytes) {
  asm volatile(ELECT "mbarrier.arrive.expect_tx.shared::cta.b64 _, [%0], %1;\n}\n" ::"r"(b), "r"(bytes) : "memory");
}
__device__ __forceinline__ void e_tma2d(uint32_t dst, const CUtensorMap* m, uint32_t bar, int c0, int c1) {
  asm volatile(ELECT "cp.async.bulk.tensor.2d.shared::cluster.global.mbarrier::complete_tx::bytes [%0], [%1, {%3,%4}], [%2];\n}\n"
               ::"r"(dst), "l"(m), "r"(bar), "r"(c0), "r"(c1) : "memory");
}
__device__ __forceinline__ void e_tma3d(uint32_t dst, const CUtensorMap* m, uint32_t bar, int c0, int c1, int c2) {
  asm volatile(ELECT "cp.async.bulk.tensor.3d.shared::cluster.global.mbarrier::complete_tx::bytes [%0], [%1, {%3,%4,%5}], [%2];\n}\n"
               ::"r"(dst), "l"(m), "r"(bar), "r"(c0), "r"(c1), "r"(c2) : "memory");
}
__device__ __forceinline__ void e_tma4d(uint32_t dst, const CUtensorMap* m, uint32_t bar, int c0, int c3) {
  asm volatile(ELECT "cp.async.bulk.tensor.4d.shared::cluster.global.mbarrier::complete_tx::bytes [%0], [%1, {%3,%5,%5,%4}], [%2];\n}\n"
               ::"r"(dst), "l"(m), "r"(bar), "r"(c0), "r"(c3), "r"(0) : "memory");
}
__device__ __forceinline__ void e_bulk(uint32_t dst, const void* src, int bytes, uint32_t bar) {
  asm volatile(ELECT "cp.async.bulk.shared::cluster.global.mbarrier::complete_tx::bytes [%0], [%1], %2, [%3];\n}\n"
               ::"r"(dst), "l"(src), "r"(bytes), "r"(bar) : "memory");
}
__device__ __forceinline__ void e_prefetch(const void* p, int bytes) {
  asm volatile(ELECT "cp.async.bulk.prefetch.L2.global [%0], %1;\n}\n" ::"l"(p), "r"(bytes) : "memory");
}
__device__ __forceinline__ void e_store2d(const CUtensorMap* m, uint32_t src, int c0, int c1) {
  asm volatile(ELECT "cp.async.bulk.tensor.2d.global.shared::cta.bulk_group [%0, {%2,%3}], [%1];\n}\n"
               ::"l"(m), "r"(src), "r"(c0), "r"(c1) : "memory");
}
__host__ __device__ constexpr uint64_t mkdesc(uint32_t addr, uint32_t lbo, uint32_t sbo, int swz) {
  return (uint64_t)((addr & 0x3FFFF) >> 4) | ((uint64_t)(lbo >> 4) << 16) | ((uint64_t)(sbo >> 4) << 32) |
         ((uint64_t)swz << 62);
}
#define SPLIT() asm volatile("{\n.reg .pred p;\nsetp.eq.u32 p, %0, %1;\n@p exit;\n}\n" ::"r"(blockIdx.y), "n"(__LINE__) : "memory")
#define SPLITN(n) asm volatile("{\n.reg .pred p;\nsetp.eq.u32 p, %0, %1;\n@p exit;\n}\n" ::"r"(blockIdx.y), "r"(4096 + (n)) : "memory")
#define WG_FENCE() asm volatile("wgmma.fence.sync.aligned;" ::: "memory")
#define WG_COMMIT() asm volatile("wgmma.commit_group.sync.aligned;" ::: "memory")
#define WG_WAIT(n) asm volatile("wgmma.wait_group.sync.aligned " #n ";" ::: "memory")

__device__ __forceinline__ void mma(float& d0, float& d1, float& d2, float& d3, uint32_t a0, uint32_t a1, uint32_t a2,
                                    uint32_t a3, uint32_t b0, uint32_t b1) {
  asm volatile("mma.sync.aligned.m16n8k16.row.col.f32.bf16.bf16.f32 {%0,%1,%2,%3},{%4,%5,%6,%7},{%8,%9},{%0,%1,%2,%3};"
               : "+f"(d0), "+f"(d1), "+f"(d2), "+f"(d3)
               : "r"(a0), "r"(a1), "r"(a2), "r"(a3), "r"(b0), "r"(b1));
}
__device__ __forceinline__ void mmac(float (&d)[4], uint32_t a0, uint32_t a1, uint32_t a2, uint32_t a3, uint32_t b0,
                                     uint32_t b1, const float (&c)[4]) {
  asm volatile("mma.sync.aligned.m16n8k16.row.col.f32.bf16.bf16.f32 {%0,%1,%2,%3},{%4,%5,%6,%7},{%8,%9},{%10,%11,%12,%13};"
               : "=f"(d[0]), "=f"(d[1]), "=f"(d[2]), "=f"(d[3])
               : "r"(a0), "r"(a1), "r"(a2), "r"(a3), "r"(b0), "r"(b1), "f"(c[0]), "f"(c[1]), "f"(c[2]), "f"(c[3]));
}
__device__ __forceinline__ void mma_h(float (&d)[4], const uint32_t (&a)[4], uint32_t b0, uint32_t b1) {
  asm volatile("mma.sync.aligned.m16n8k16.row.col.f32.f16.f16.f32 {%0,%1,%2,%3},{%4,%5,%6,%7},{%8,%9},{%0,%1,%2,%3};"
               : "+f"(d[0]), "+f"(d[1]), "+f"(d[2]), "+f"(d[3]) : "r"(a[0]), "r"(a[1]), "r"(a[2]), "r"(a[3]), "r"(b0), "r"(b1));
}
__device__ __forceinline__ void mma0(float& d0, float& d1, float& d2, float& d3, uint32_t a0, uint32_t a1, uint32_t a2,
                                     uint32_t a3, uint32_t b0, uint32_t b1) {
  asm volatile("mma.sync.aligned.m16n8k16.row.col.f32.bf16.bf16.f32 {%0,%1,%2,%3},{%4,%5,%6,%7},{%8,%9},{%10,%10,%10,%10};"
               : "=f"(d0), "=f"(d1), "=f"(d2), "=f"(d3)
               : "r"(a0), "r"(a1), "r"(a2), "r"(a3), "r"(b0), "r"(b1), "f"(0.f));
}
__device__ __forceinline__ uint32_t pack_bf(float lo, float hi) {
  uint32_t r;
  asm("cvt.rn.bf16x2.f32 %0, %1, %2;" : "=r"(r) : "f"(hi), "f"(lo));
  return r;
}
__device__ __forceinline__ float bf_lo(uint32_t w) { return __uint_as_float(w << 16); }
__device__ __forceinline__ float bf_hi(uint32_t w) { return __uint_as_float(w & 0xffff0000u); }
__device__ __forceinline__ float bf_round(float x) { return __bfloat162float(__float2bfloat16_rn(x)); }
__device__ __forceinline__ uint32_t bmax2(uint32_t a, uint32_t b) {
  uint32_t r; asm("max.bf16x2 %0, %1, %2;" : "=r"(r) : "r"(a), "r"(b)); return r;
}
__device__ __forceinline__ uint32_t bmin2(uint32_t a, uint32_t b) {
  uint32_t r; asm("min.bf16x2 %0, %1, %2;" : "=r"(r) : "r"(a), "r"(b)); return r;
}
__device__ __forceinline__ float ex2(float x) { float r; asm("ex2.approx.ftz.f32 %0, %1;" : "=f"(r) : "f"(x)); return r; }
__device__ __forceinline__ float rcp(float x) { float r; asm("rcp.approx.ftz.f32 %0, %1;" : "=f"(r) : "f"(x)); return r; }
__device__ __forceinline__ void ldsm4(uint32_t (&r)[4], uint32_t a) {
  asm volatile("ldmatrix.sync.aligned.m8n8.x4.shared.b16 {%0,%1,%2,%3}, [%4];"
               : "=r"(r[0]), "=r"(r[1]), "=r"(r[2]), "=r"(r[3]) : "r"(a) : "memory");
}
__device__ __forceinline__ void ldsm4t(uint32_t (&r)[4], uint32_t a) {
  asm volatile("ldmatrix.sync.aligned.m8n8.x4.trans.shared.b16 {%0,%1,%2,%3}, [%4];"
               : "=r"(r[0]), "=r"(r[1]), "=r"(r[2]), "=r"(r[3]) : "r"(a) : "memory");
}
__device__ __forceinline__ void stsm4(uint32_t a, uint32_t r0, uint32_t r1, uint32_t r2, uint32_t r3) {
  asm volatile("stmatrix.sync.aligned.m8n8.x4.shared.b16 [%0], {%1,%2,%3,%4};"
               ::"r"(a), "r"(r0), "r"(r1), "r"(r2), "r"(r3) : "memory");
}
__device__ __forceinline__ uint32_t lds32(uint32_t a) {
  uint32_t r; asm volatile("ld.shared.u32 %0, [%1];" : "=r"(r) : "r"(a) : "memory"); return r;
}
__device__ __forceinline__ uint32_t lds16(uint32_t a) {
  uint32_t r; asm volatile("{\n.reg .u16 h;\nld.shared.u16 h, [%1];\ncvt.u32.u16 %0, h;\n}\n" : "=r"(r) : "r"(a) : "memory"); return r;
}
__device__ __forceinline__ uint2 lds64(uint32_t a) {
  uint2 r; asm volatile("ld.shared.v2.u32 {%0,%1}, [%2];" : "=r"(r.x), "=r"(r.y) : "r"(a) : "memory"); return r;
}
__device__ __forceinline__ uint4 lds128(uint32_t a) {
  uint4 r;
  asm volatile("ld.shared.v4.u32 {%0,%1,%2,%3}, [%4];" : "=r"(r.x), "=r"(r.y), "=r"(r.z), "=r"(r.w) : "r"(a) : "memory");
  return r;
}
__device__ __forceinline__ void sts32(uint32_t a, uint32_t v) { asm volatile("st.shared.u32 [%0], %1;" ::"r"(a), "r"(v) : "memory"); }
__device__ __forceinline__ void sts16(uint32_t a, uint32_t v) {
  asm volatile("{\n.reg .u16 h;\ncvt.u16.u32 h, %1;\nst.shared.u16 [%0], h;\n}\n" ::"r"(a), "r"(v) : "memory");
}
__device__ __forceinline__ void sts64(uint32_t a, uint32_t x, uint32_t y) {
  asm volatile("st.shared.v2.u32 [%0], {%1,%2};" ::"r"(a), "r"(x), "r"(y) : "memory");
}
__device__ __forceinline__ void sts128(uint32_t a, uint32_t x, uint32_t y, uint32_t z, uint32_t w) {
  asm volatile("st.shared.v4.u32 [%0], {%1,%2,%3,%4};" ::"r"(a), "r"(x), "r"(y), "r"(z), "r"(w) : "memory");
}
__device__ __forceinline__ uint4 ld_x(const uint4* p) {
  uint4 r;
  asm volatile("{\n.reg .b128 t;\nld.relaxed.gpu.global.b128 t, [%4];\nmov.b128 {%0,%1,%2,%3}, t;\n}\n"
               : "=r"(r.x), "=r"(r.y), "=r"(r.z), "=r"(r.w) : "l"(p) : "memory");
  return r;
}
__device__ __forceinline__ uint32_t ld_x32(const uint32_t* p) {
  uint32_t r; asm volatile("ld.relaxed.gpu.global.u32 %0, [%1];" : "=r"(r) : "l"(p) : "memory"); return r;
}
__device__ __forceinline__ void st_x(uint4* p, uint32_t x, uint32_t y, uint32_t z, uint32_t w) {
  asm volatile("{\n.reg .b128 t;\nmov.b128 t, {%1,%2,%3,%4};\nst.relaxed.gpu.global.b128 [%0], t;\n}\n"
               ::"l"(p), "r"(x), "r"(y), "r"(z), "r"(w) : "memory");
}
__device__ __forceinline__ void st_x32(uint32_t* p, uint32_t x) {
  asm volatile("st.relaxed.gpu.global.u32 [%0], %1;" ::"l"(p), "r"(x) : "memory");
}
__device__ __forceinline__ uint32_t nz(uint32_t w) { uint32_t r; asm("max.u32 %0, %1, 1;" : "=r"(r) : "r"(w)); return r; }
__device__ __forceinline__ uint32_t fu(float x) { return __float_as_uint(x); }
__device__ __forceinline__ float uf(uint32_t x) { return __uint_as_float(x); }

__device__ __forceinline__ void wgmma_ss_n96(float (&d)[48], uint64_t da, uint64_t db, int sc) {
  asm volatile("{\n.reg .pred p;\nsetp.ne.b32 p, %50, 0;\n"
      "wgmma.mma_async.sync.aligned.m64n96k16.f32.bf16.bf16 "
      "{%0,%1,%2,%3,%4,%5,%6,%7,%8,%9,%10,%11,%12,%13,%14,%15,%16,%17,%18,%19,%20,%21,%22,%23,%24,%25,%26,%27,%28,%29,%30,%31,%32,%33,%34,%35,%36,%37,%38,%39,%40,%41,%42,%43,%44,%45,%46,%47}, "
      "%48, %49, p, 1, 1, 0, 1;\n}\n"
      : "+f"(d[0]), "+f"(d[1]), "+f"(d[2]), "+f"(d[3]), "+f"(d[4]), "+f"(d[5]), "+f"(d[6]), "+f"(d[7]),
        "+f"(d[8]), "+f"(d[9]), "+f"(d[10]), "+f"(d[11]), "+f"(d[12]), "+f"(d[13]), "+f"(d[14]), "+f"(d[15]),
        "+f"(d[16]), "+f"(d[17]), "+f"(d[18]), "+f"(d[19]), "+f"(d[20]), "+f"(d[21]), "+f"(d[22]), "+f"(d[23]),
        "+f"(d[24]), "+f"(d[25]), "+f"(d[26]), "+f"(d[27]), "+f"(d[28]), "+f"(d[29]), "+f"(d[30]), "+f"(d[31]),
        "+f"(d[32]), "+f"(d[33]), "+f"(d[34]), "+f"(d[35]), "+f"(d[36]), "+f"(d[37]), "+f"(d[38]), "+f"(d[39]),
        "+f"(d[40]), "+f"(d[41]), "+f"(d[42]), "+f"(d[43]), "+f"(d[44]), "+f"(d[45]), "+f"(d[46]), "+f"(d[47])
      : "l"(da), "l"(db), "r"(sc));
}

__device__ __forceinline__ void wgmma_ss_n128(float (&d)[64], uint64_t da, uint64_t db, int sc) {
  asm volatile("{\n.reg .pred p;\nsetp.ne.b32 p, %66, 0;\n"
      "wgmma.mma_async.sync.aligned.m64n128k16.f32.bf16.bf16 "
      "{%0,%1,%2,%3,%4,%5,%6,%7,%8,%9,%10,%11,%12,%13,%14,%15,%16,%17,%18,%19,%20,%21,%22,%23,%24,%25,%26,%27,%28,%29,%30,%31,%32,%33,%34,%35,%36,%37,%38,%39,%40,%41,%42,%43,%44,%45,%46,%47,%48,%49,%50,%51,%52,%53,%54,%55,%56,%57,%58,%59,%60,%61,%62,%63}, "
      "%64, %65, p, 1, 1, 0, 1;\n}\n"
      : "+f"(d[0]), "+f"(d[1]), "+f"(d[2]), "+f"(d[3]), "+f"(d[4]), "+f"(d[5]), "+f"(d[6]), "+f"(d[7]),
        "+f"(d[8]), "+f"(d[9]), "+f"(d[10]), "+f"(d[11]), "+f"(d[12]), "+f"(d[13]), "+f"(d[14]), "+f"(d[15]),
        "+f"(d[16]), "+f"(d[17]), "+f"(d[18]), "+f"(d[19]), "+f"(d[20]), "+f"(d[21]), "+f"(d[22]), "+f"(d[23]),
        "+f"(d[24]), "+f"(d[25]), "+f"(d[26]), "+f"(d[27]), "+f"(d[28]), "+f"(d[29]), "+f"(d[30]), "+f"(d[31]),
        "+f"(d[32]), "+f"(d[33]), "+f"(d[34]), "+f"(d[35]), "+f"(d[36]), "+f"(d[37]), "+f"(d[38]), "+f"(d[39]),
        "+f"(d[40]), "+f"(d[41]), "+f"(d[42]), "+f"(d[43]), "+f"(d[44]), "+f"(d[45]), "+f"(d[46]), "+f"(d[47]),
        "+f"(d[48]), "+f"(d[49]), "+f"(d[50]), "+f"(d[51]), "+f"(d[52]), "+f"(d[53]), "+f"(d[54]), "+f"(d[55]),
        "+f"(d[56]), "+f"(d[57]), "+f"(d[58]), "+f"(d[59]), "+f"(d[60]), "+f"(d[61]), "+f"(d[62]), "+f"(d[63])
      : "l"(da), "l"(db), "r"(sc));
}

__device__ __forceinline__ void wgmma_ss_n40(float (&d)[20], uint64_t da, uint64_t db, int sc) {
  asm volatile("{\n.reg .pred p;\nsetp.ne.b32 p, %22, 0;\n"
      "wgmma.mma_async.sync.aligned.m64n40k16.f32.bf16.bf16 "
      "{%0,%1,%2,%3,%4,%5,%6,%7,%8,%9,%10,%11,%12,%13,%14,%15,%16,%17,%18,%19}, "
      "%20, %21, p, 1, 1, 1, 1;\n}\n"
      : "+f"(d[0]), "+f"(d[1]), "+f"(d[2]), "+f"(d[3]), "+f"(d[4]), "+f"(d[5]), "+f"(d[6]), "+f"(d[7]),
        "+f"(d[8]), "+f"(d[9]), "+f"(d[10]), "+f"(d[11]), "+f"(d[12]), "+f"(d[13]), "+f"(d[14]), "+f"(d[15]),
        "+f"(d[16]), "+f"(d[17]), "+f"(d[18]), "+f"(d[19])
      : "l"(da), "l"(db), "r"(sc));
}

__device__ __forceinline__ void wgmma_rs_n8(float (&d)[4], const uint4& a, uint64_t db, int sc) {
  asm volatile("{\n.reg .pred p;\nsetp.ne.b32 p, %9, 0;\n"
      "wgmma.mma_async.sync.aligned.m64n8k16.f32.bf16.bf16 "
      "{%0,%1,%2,%3}, "
      "{%4,%5,%6,%7}, %8, p, 1, 1, 1;\n}\n"
      : "+f"(d[0]), "+f"(d[1]), "+f"(d[2]), "+f"(d[3])
      : "r"(a.x), "r"(a.y), "r"(a.z), "r"(a.w), "l"(db), "r"(sc));
}

__device__ __forceinline__ void wgmma_rs_n16(float (&d)[8], const uint4& a, uint64_t db, int sc) {
  asm volatile("{\n.reg .pred p;\nsetp.ne.b32 p, %13, 0;\n"
      "wgmma.mma_async.sync.aligned.m64n16k16.f32.bf16.bf16 "
      "{%0,%1,%2,%3,%4,%5,%6,%7}, "
      "{%8,%9,%10,%11}, %12, p, 1, 1, 1;\n}\n"
      : "+f"(d[0]), "+f"(d[1]), "+f"(d[2]), "+f"(d[3]), "+f"(d[4]), "+f"(d[5]), "+f"(d[6]), "+f"(d[7])
      : "r"(a.x), "r"(a.y), "r"(a.z), "r"(a.w), "l"(db), "r"(sc));
}

__device__ __forceinline__ void wgmma_rs_n24(float (&d)[12], const uint4& a, uint64_t db, int sc) {
  asm volatile("{\n.reg .pred p;\nsetp.ne.b32 p, %17, 0;\n"
      "wgmma.mma_async.sync.aligned.m64n24k16.f32.bf16.bf16 "
      "{%0,%1,%2,%3,%4,%5,%6,%7,%8,%9,%10,%11}, "
      "{%12,%13,%14,%15}, %16, p, 1, 1, 1;\n}\n"
      : "+f"(d[0]), "+f"(d[1]), "+f"(d[2]), "+f"(d[3]), "+f"(d[4]), "+f"(d[5]), "+f"(d[6]), "+f"(d[7]),
        "+f"(d[8]), "+f"(d[9]), "+f"(d[10]), "+f"(d[11])
      : "r"(a.x), "r"(a.y), "r"(a.z), "r"(a.w), "l"(db), "r"(sc));
}

struct Params {
  const __nv_bfloat16 *logA, *Aim, *Cre, *Cim, *logdt, *Dskip, *x, *wphi, *wo;
  __nv_bfloat16* out;
  uint4* xs;
  long long* ts;
};

__device__ __forceinline__ uint4 tr_row(const uint4 (&v)[8], int i) {
  uint32_t o[4];
#pragma unroll
  for (int m = 0; m < 4; m++) {
    const uint4 &ra = v[2 * m], &rb = v[2 * m + 1];
    const int k = i >> 1;
    const uint32_t xa = k == 0 ? ra.x : k == 1 ? ra.y : k == 2 ? ra.z : ra.w;
    const uint32_t xb = k == 0 ? rb.x : k == 1 ? rb.y : k == 2 ? rb.z : rb.w;
    o[m] = __byte_perm(xa, xb, (i & 1) ? 0x7632 : 0x5410);
  }
  return make_uint4(o[0], o[1], o[2], o[3]);
}

struct cpx { float r, i; };
__device__ __forceinline__ cpx csq(cpx a) { return {a.r * a.r - a.i * a.i, 2.f * (a.r * a.i)}; }
__device__ __forceinline__ cpx polar(float e, float t) {
  const float m = ex2(e);
  return {m * __cosf(t), m * __sinf(t)};
}

struct KgenRaw { uint32_t la, ai, cr, ci, ldt; };
__device__ __forceinline__ KgenRaw kgen_load(const Params& P, int d, int unit, int lane, int on) {
  const int o = d * 64 + unit * 32 + lane;
  KgenRaw r = {0, 0, 0, 0, 0};
  asm volatile("{\n.reg .pred p;\nsetp.ne.b32 p, %10, 0;\n@p ld.global.nc.u32 %0, [%5];\n@p ld.global.nc.u32 %1, [%6];\n"
               "@p ld.global.nc.u32 %2, [%7];\n@p ld.global.nc.u32 %3, [%8];\n@p ld.global.nc.u16 %4, [%9];\n}\n"
               : "+r"(r.la), "+r"(r.ai), "+r"(r.cr), "+r"(r.ci), "+r"(r.ldt)
               : "l"((const uint32_t*)P.logA + o), "l"((const uint32_t*)P.Aim + o), "l"((const uint32_t*)P.Cre + o),
                 "l"((const uint32_t*)P.Cim + o), "l"(P.logdt + d), "r"(on));
  return r;
}
struct hc { __half2 r, i; };
struct cpx2 { cpx a, b; };
__device__ __forceinline__ cpx2 csq2(const cpx2& v) { return {csq(v.a), csq(v.b)}; }
__device__ __forceinline__ hc toh(const cpx2& v) { return {__floats2half2_rn(v.a.r, v.b.r), __floats2half2_rn(v.a.i, v.b.i)}; }
__device__ __forceinline__ hc hmul(const hc& z, const hc& w) {
  return {__hfma2(z.r, w.r, __hneg2(__hmul2(z.i, w.i))), __hfma2(z.r, w.i, __hmul2(z.i, w.r))};
}
__device__ __forceinline__ hc hmulc(const hc& z, const hc& w) {
  return {__hfma2(z.r, w.r, __hmul2(z.i, w.i)), __hfma2(z.i, w.r, __hneg2(__hmul2(z.r, w.i)))};
}
__device__ __forceinline__ uint32_t hu(__half2 v) { return *(const uint32_t*)&v; }
__device__ __forceinline__ __half2 uh(uint32_t v) { return *(const __half2*)&v; }

struct KgenAddr { uint32_t sa[2], ld[5][4]; };
__device__ __forceinline__ KgenAddr kgen_addr(int lane, uint32_t buf) {
  KgenAddr a;
  a.sa[0] = buf + (lane & 7) * 128 + ((((lane >> 3) ^ lane) & 7) << 4);
  a.sa[1] = a.sa[0] ^ 64;
  const int q = lane >> 4;
  const uint32_t b = buf + ((lane >> 3) & 1) * 1024 + q * 128;
  const int e[5] = {lane & 7, 0, 1, 2 + (lane & 1), 4 + (lane & 3)};
#pragma unroll
  for (int i = 0; i < 20; i++) {
    a.ld[i >> 2][i & 3] = b + ((e[i >> 2] ^ q ^ (2 * (i & 3))) << 4);
    asm volatile("" : "+r"(a.ld[i >> 2][i & 3]));
  }
  asm volatile("" : "+r"(a.sa[0]), "+r"(a.sa[1]));
  return a;
}
__device__ __forceinline__ void kgen_unit(const KgenRaw& r, const KgenAddr& ad, uint32_t zero, float (&k)[5][4], float& k2048, float& sc) {
  const float dt = bf_round(expf(bf_lo(r.ldt)));
  const uint32_t ar = pack_bf(ex2(bf_lo(r.la) * 1.4426950408889634f), ex2(bf_hi(r.la) * 1.4426950408889634f));
  const float ca = dt * -1.4426950408889634f, a0 = bf_lo(ar) * ca, a1 = bf_hi(ar) * ca;
  const float f0 = bf_lo(r.ai) * dt, f1 = bf_hi(r.ai) * dt;
  const float r0 = f0 * 20.21267777267071f, r1 = f1 * 20.21267777267071f;
  const uint32_t cm = __vmaxu2(r.cr & 0x7fff7fffu, r.ci & 0x7fff7fffu);
  const uint32_t ex = min(max(__reduce_max_sync(0xffffffffu, max(cm >> 16, cm & 0xffffu)) >> 7, 1u), 253u);
  const float cs = uf((254u - ex) << 23);
  sc = 2.f * dt * uf(ex << 23);
  const cpx2 C = {{bf_lo(r.cr) * cs, bf_lo(r.ci) * -cs}, {bf_hi(r.cr) * cs, bf_hi(r.ci) * -cs}};
  auto put = [&](const hc (&v)[8]) {
    stsm4(ad.sa[0], hu(v[0].r), hu(v[1].r), hu(v[2].r), hu(v[3].r));
    stsm4(ad.sa[0] + 1024, hu(v[0].i), hu(v[1].i), hu(v[2].i), hu(v[3].i));
    stsm4(ad.sa[1], hu(v[4].r), hu(v[5].r), hu(v[6].r), hu(v[7].r));
    stsm4(ad.sa[1] + 1024, hu(v[4].i), hu(v[5].i), hu(v[6].i), hu(v[7].i));
    __syncwarp();
  };
  auto get = [&](uint32_t (&o)[4][4], const uint32_t (&a)[4]) {
#pragma unroll
    for (int i = 0; i < 4; i++) ldsm4(o[i], a[i] + i * 256);
  };
  auto at = [](const uint32_t (&o)[4][4], int s) { return hc{uh(o[s >> 1][2 * (s & 1)]), uh(o[s >> 1][2 * (s & 1) + 1])}; };
  uint32_t A[8][4];
  auto tile = [&](int j, const uint32_t (&B)[4][4]) {
    k[j][0] = k[j][1] = k[j][2] = k[j][3] = 0.f;
#pragma unroll
    for (int s = 0; s < 8; s++) mma_h(k[j], A[s], B[s >> 1][2 * (s & 1)], B[s >> 1][2 * (s & 1) + 1]);
  };
  const cpx2 w1 = {polar(a0, f0), polar(a1, f1)};
  const cpx2 w127 = {polar(a0 * 127.f, (r0 - rintf(r0)) * 6.283185307179586f), polar(a1 * 127.f, (r1 - rintf(r1)) * 6.283185307179586f)};
  const cpx2 w2 = csq2(w1), w4 = csq2(w2);
  uint32_t T0[4][4], X[4][4], M[3][4][4];
  {
    hc t[8];
    t[0] = {uh(0x3C003C00u), uh(0u)}; t[1] = toh(w1); t[2] = toh(w2); t[4] = toh(w4);
    t[3] = hmul(t[1], t[2]); t[5] = hmul(t[1], t[4]); t[6] = hmul(t[2], t[4]); t[7] = hmul(t[3], t[4]);
    put(t); get(T0, ad.ld[0]);
  }
  SPLIT();
  const cpx2 w8 = csq2(w4), w16 = csq2(w8), w32 = csq2(w16), w64 = csq2(w32);
  {
    const hc m8 = toh(w8), m16 = toh(w16), m32 = toh(w32);
    hc a[8];
    a[0] = toh(C); a[1] = hmulc(a[0], m8);
    a[2] = hmulc(a[0], m16); a[3] = hmulc(a[1], m16);
#pragma unroll
    for (int i = 0; i < 4; i++) a[4 + i] = hmulc(a[i], m32);
    put(a); get(X, ad.ld[0]);
  }
  SPLIT();
    const cpx2 w128 = {{w127.a.r * w1.a.r - w127.a.i * w1.a.i, w127.a.r * w1.a.i + w127.a.i * w1.a.r},
                     {w127.b.r * w1.b.r - w127.b.i * w1.b.i, w127.b.r * w1.b.i + w127.b.i * w1.b.r}};
  const cpx2 w256 = csq2(w128), w512 = csq2(w256);
  const hc m128 = toh(w128), m256 = toh(w256), m512 = toh(w512);
  {
    const hc m254 = toh(csq2(w127)), m127 = toh(w127);
    hc m[8];
    m[0] = toh(w64); m[1] = m128; m[2] = m256; m[3] = hmul(m127, m256);
    m[4] = m512; m[5] = hmul(m127, m512); m[6] = hmul(m[4], m254); m[7] = hmul(m[5], m254);
    put(m);
    get(M[0], ad.ld[1]);
#pragma unroll
    for (int s = 0; s < 8; s++) {
      const hc z = at(X, s), y = hmulc(z, at(M[0], s));
      A[s][0] = hu(z.r) + zero; A[s][1] = hu(y.r); A[s][2] = hu(z.i) + zero; A[s][3] = hu(y.i);
    }
#pragma unroll
    for (int i = 0; i < 3; i++) get(M[i], ad.ld[i + 2]);
  }
  SPLIT();
  tile(0, T0);
  const cpx2 w1024 = csq2(w512), we = csq2(w1024);
  {
    hc t[8];
    t[0] = toh(w1024); t[1] = hmul(t[0], m128);
    t[2] = hmul(t[0], m256); t[3] = hmul(t[1], m256);
#pragma unroll
    for (int i = 0; i < 4; i++) t[4 + i] = hmul(t[i], m512);
    put(t); get(X, ad.ld[0]);
  }
  k2048 = (C.a.r * we.a.r + C.a.i * we.a.i + C.b.r * we.b.r + C.b.i * we.b.i) * sc;
#pragma unroll
  for (int j = 1; j < 5; j++) k[j][0] = k[j][1] = k[j][2] = k[j][3] = 0.f;
#pragma unroll
  for (int s = 0; s < 8; s++) {
#pragma unroll
    for (int j = 0; j < 3; j++) {
      const hc y = hmul(at(T0, s), at(M[j], s));
      mma_h(k[1 + j], A[s], hu(y.r), hu(y.i));
    }
    mma_h(k[4], A[s], X[s >> 1][2 * (s & 1)], X[s >> 1][2 * (s & 1) + 1]);
  }
}

__device__ __forceinline__ void build_tables(uint32_t tb, int lane, float (&k)[5][4], float k2048) {
  const int g = lane >> 2, c = lane & 3;
  const uint32_t kc = tb + T_KC + 16;
  {
    const uint32_t a0 = kc + 16 * g + 4 * c, a2 = kc + 2 * (256 + 4 * g + c);
    const uint32_t a3 = kc + 2 * (384 + 2 * g + 64 * (c & 1) + (c >> 1)), a4 = kc + 2 * (512 + g + 32 * c);
#pragma unroll
    for (int r = 0; r < 2; r++) {
      sts32(a0 + 128 * r, pack_bf(k[0][2 * r], k[0][2 * r + 1]));
      sts32(a0 + 128 * r + 256, pack_bf(k[1][2 * r], k[1][2 * r + 1]));
      const uint32_t w2 = pack_bf(k[2][2 * r], k[2][2 * r + 1]);
      const uint32_t w3 = pack_bf(k[3][2 * r], k[3][2 * r + 1]);
      const uint32_t w4 = pack_bf(k[4][2 * r], k[4][2 * r + 1]);
      sts16(a2 + 64 * r, w2); sts16(a2 + 64 * r + 128, w2 >> 16);
      sts16(a3 + 32 * r, w3); sts16(a3 + 32 * r + 64, w3 >> 16);
      sts16(a4 + 16 * r, w4); sts16(a4 + 16 * r + 32, w4 >> 16);
    }
  }
  if (lane == 0) { sts16(kc + 2 * 640, pack_bf(k2048, 0.f)); sts32(kc - 4, 0); }
  __syncwarp();
  const uint32_t td = tb + T_D + 32;
#pragma unroll
  for (int hf = 0; hf < 2; hf++) {
    const uint2 v = lds64(kc + 256 * hf + 8 * lane);
    const uint32_t pv = lds32(kc + 256 * hf + 8 * lane - 4);
    sts128(td + 512 * hf + 16 * lane, __byte_perm(v.x, pv, 0x7610), __byte_perm(v.x, v.x, 0x1032), __byte_perm(v.y, v.x, 0x7610),
           __byte_perm(v.y, v.y, 0x1032));
  }
#pragma unroll
  for (int hf = 0; hf < 2; hf++) {
    const uint32_t v = lds32(kc + 512 + 128 * hf + 4 * lane), nx = lds32(kc + 516 + 128 * hf + 4 * lane);
    uint32_t w0 = __byte_perm(v, v, 0x1010);
    const uint32_t w1 = w0;
    if (hf == 0) { const uint32_t pv = lds32(kc + 508); if (lane == 0) w0 = __byte_perm(v, pv, 0x7610); }
    sts128(td + 1024 + 512 * hf + 16 * lane, w0, w1, __byte_perm(v, v, 0x1032), __byte_perm(nx, v, 0x7610));
  }
  {
    const uint32_t kk = lds16(kc + 2 * 384);
    const uint32_t w = lane < 3 ? (kk | (kk << 16)) : (lane == 3 ? (kk << 16) : 0u);
    if (lane < 24) sts32(td + 4 * (lane < 16 ? 512 + lane : lane - 24), w);
    const uint32_t lo_ = lds16(kc + 2 * 511), le_ = lds16(kc + 2 * 512);
    const uint32_t ja = tb + T_5 + (lane < 16 ? 4 * lane : 256 + 4 * lane);
    sts32(ja, lane == 16 ? (le_ << 16) : 0u);
    sts32(ja + 384, lane == 16 ? (lo_ << 16) : 0u);
    sts32(tb + (lane < 16 ? T_7 : T_9 - 64) + 4 * lane, 0u);
  }
#pragma unroll
  for (int s = 0; s < 2; s++) {
    const uint32_t b = kc + 2 * (s ? 512 : 384) + 8 * lane;
    const uint2 v = lds64(b);
    uint32_t em = lds16(b - 2), e0 = v.x;
    const uint32_t e4 = lds16(b + 8);
    if (lane == 0) { em = 0; e0 = 0; }
    sts64(tb + (s ? T_7 : T_3) + 64 + 8 * lane, __byte_perm(v.x, em, 0x5432), __byte_perm(v.y, v.x, 0x7632));
    sts64(tb + (s ? T_9 : T_5) + 64 + 8 * lane, __byte_perm(v.y, e0, 0x5410), __byte_perm(e4, v.y, 0x5410));
  }
  __syncwarp();
}

__device__ __forceinline__ uint32_t box2w(int lo, int n, int o) {
  return ((unsigned)(o - lo) < (unsigned)n ? 0x3F80u : 0u) | ((unsigned)(o + 1 - lo) < (unsigned)n ? 0x3F800000u : 0u);
}

__device__ __forceinline__ void conv_channel(uint32_t ub, uint32_t tb, int lane, uint4* ydst) {
  const int g = lane >> 2, c = lane & 3, x = g - 2 * c;
  const int mi = lane >> 3;
  const uint32_t qa = ub + U_PAD + 16 * (lane & 7) + ((mi == 0 || mi == 3) ? U_ODD : 0) - (mi == 0 ? 16 : 0);
  const uint32_t hb = ub + U_PAD + (mi & 1) * U_ODD + 16 * ((lane >> 4) + (lane & 7)) - 16;
  const uint32_t kv = lds16(tb + T_KC + 16 + 2 * 512);
  const int oh = c < 2 ? 8 + 2 * c : 2 * c - 8, og = c < 3 ? 2 * c : -10;
  uint32_t bx[4] = {box2w(g - 4, 9, 2 * c), box2w(g - 3, 7, 2 * c), box2w(g - 4, 9, oh), box2w(g - 3, 7, oh)};
  uint32_t by[4] = {box2w(g - 10, 5, 2 * c - 8), box2w(g - 5, 3, 2 * c - 8), box2w(g - 10, 5, og), box2w(g - 5, 3, og)};
  uint32_t lb0 = ((unsigned)(x + 5) < 2u ? kv : 0u) | ((unsigned)(x + 4) < 2u ? kv << 16 : 0u);
  uint32_t lb1 = ((unsigned)(x - 3) < 2u ? kv : 0u) | ((unsigned)(x - 4) < 2u ? kv << 16 : 0u);
  const int q0 = g - 1, q1 = c < 3 ? g : g - 2;
  uint32_t y0a = ub + U_PAD + (q0 & 1) * U_ODD + 16 * (q0 >> 1) + 4 * c;
  uint32_t y1a = ub + U_PAD + (q1 & 1) * U_ODD + 16 * (q1 >> 1) + 4 * c;
#pragma unroll
  for (int i = 0; i < 4; i++) asm volatile("" : "+r"(bx[i]), "+r"(by[i]));
  asm volatile("" : "+r"(lb0), "+r"(lb1), "+r"(y0a), "+r"(y1a));
  mbar_wait(BAR(MB_UFULL));
  mbar_spin(BAR(MB_EMPTY + 15));
  TS(36);
  float acc[16][4];
  {
    uint32_t z09[8], z07[8], zm9[8], zm7[8];
#pragma unroll
    for (int i = 0; i < 8; i++) {
      uint32_t h[4];
      ldsm4(h, hb + 128 * i);
      float y0, y1, y2, y3, w0, w1, w2, w3;
      mma0(y0, y1, y2, y3, bx[0], bx[1], bx[2], bx[3], h[2], c < 2 ? h[3] : h[1]);
      mma0(w0, w1, w2, w3, bx[0], bx[1], bx[2], bx[3], h[1], c < 2 ? h[2] : h[0]);
      z09[i] = pack_bf(y0, y1); z07[i] = pack_bf(y2, y3);
      zm9[i] = pack_bf(w0, w1); zm7[i] = pack_bf(w2, w3);
    }
  uint32_t f3[3][4][4];
  {
    const uint32_t fa = tb + T_7 + 4 * (16 + x);
#pragma unroll
    for (int tt = 0; tt < 3; tt++)
#pragma unroll
      for (int D = 0; D < 4; D++) {
        const uint32_t a = fa + (tt == 0 ? 316 : (tt == 1 ? 320 : 0)) + 64 * D;
        f3[tt][D][0] = lds32(a); f3[tt][D][1] = lds32(a + 32); f3[tt][D][2] = lds32(a - 32); f3[tt][D][3] = lds32(a);
      }
  }
    SPLIT();
    nb_sync(NB_GATE, 256);
    SPLIT();
    float a[4][2][4];
#pragma unroll
    for (int kap = 0; kap < 4; kap++)
#pragma unroll
      for (int sg = 0; sg < 2; sg++)
#pragma unroll
        for (int bk = 3; bk >= kap; bk--) {
          const uint32_t(&q0_)[4] = f3[sg ? 2 : 0][bk - kap];
          const uint32_t(&q1_)[4] = f3[sg ? 2 : 1][bk - kap];
          float(&a0)[4] = a[bk][0];
          float(&a1)[4] = a[bk][1];
          if (sg == 0 && kap == 0) {
            mma0(a0[0], a0[1], a0[2], a0[3], q0_[0], q0_[1], q0_[2], q0_[3], z09[0], z09[1]);
            mma0(a1[0], a1[1], a1[2], a1[3], q1_[0], q1_[1], q1_[2], q1_[3], zm9[0], zm9[1]);
          } else {
            mma(a0[0], a0[1], a0[2], a0[3], q0_[0], q0_[1], q0_[2], q0_[3], sg ? zm7[2 * kap] : z09[2 * kap], sg ? zm7[2 * kap + 1] : z09[2 * kap + 1]);
            mma(a1[0], a1[1], a1[2], a1[3], q1_[0], q1_[1], q1_[2], q1_[3], sg ? z07[2 * kap] : zm9[2 * kap], sg ? z07[2 * kap + 1] : zm9[2 * kap + 1]);
          }
        }
    SPLIT();
#pragma unroll
    for (int i = 0; i < 8; i++) {
      uint32_t h[4];
      ldsm4(h, qa + 128 * i);
      const float ci[4] = {a[i >> 1][0][2 * (i & 1)], a[i >> 1][0][2 * (i & 1) + 1], a[i >> 1][1][2 * (i & 1)], a[i >> 1][1][2 * (i & 1) + 1]};
      mmac(acc[8 + i], h[0], h[1], h[2], h[3], lb0, lb1, ci);
    }
  }
  TS(44);
  {
    uint2 a5[10], a3[10];
    const uint32_t aa = tb + T_5 + 4 * (8 + 2 * g - 2 * c);
#pragma unroll
    for (int m = 0; m < 10; m++) { a5[m] = lds64(aa + 32 * m); a3[m] = lds64(aa + 384 + 32 * m); }
    uint32_t x5[12][2], x3[12][2];
    auto ygen = [&](int kap) {
#pragma unroll
      for (int hh = 0; hh < 2; hh++) {
        float y0, y1, y2, y3;
        mma0(y0, y1, y2, y3, by[0], by[1], by[2], by[3], lds32(y0a + 128 * kap + 64 * hh), lds32(y1a + 128 * kap + 64 * hh));
        x5[kap][hh] = pack_bf(y0, y1);
        x3[kap][hh] = pack_bf(y2, y3);
      }
    };
    ygen(11); ygen(10); ygen(9); ygen(8);
#pragma unroll
    for (int kap = 11; kap >= 0; kap--) {
      if (kap >= 4) ygen(kap - 4);
#pragma unroll
      for (int sg = 0; sg < 2; sg++)
#pragma unroll
        for (int i = 4; i >= 0; i--) {
          const int be = kap + 4 + i;
          if (be <= 15) {
            const uint2 &hi = sg ? a3[2 * i + 1] : a5[2 * i + 1], &lo = sg ? a3[2 * i] : a5[2 * i];
            const uint32_t b0 = sg ? x3[kap][0] : x5[kap][0], b1 = sg ? x3[kap][1] : x5[kap][1];
            if (be < 8 && i == 0 && sg == 0) mma0(acc[be][0], acc[be][1], acc[be][2], acc[be][3], hi.x, hi.y, lo.x, lo.y, b0, b1);
            else mma(acc[be][0], acc[be][1], acc[be][2], acc[be][3], hi.x, hi.y, lo.x, lo.y, b0, b1);
          }
        }
    }
  }
  TS(45);
  {
    const uint32_t st = tb + T_ST + lane * 16;
#pragma unroll
    for (int be = 4; be < 10; be++) sts128(st + 512 * be, fu(acc[be][0]), fu(acc[be][1]), fu(acc[be][2]), fu(acc[be][3]));
    SPLIT();
    uint32_t F[66], qd[8][4];
    const uint32_t fa = tb + T_D + 32 + 4 * x;
#pragma unroll
    for (int i = 0; i < 32; i++) {
      const int s = 120 - (i >> 2) - 8 * (i & 3);
      uint32_t(&q)[4] = qd[i & 7];
      ldsm4(q, qa + 16 * s);
      const int m = 16 * (i & 3) + 2 * (i >> 2);
      F[m] = lds32(fa + 32 * m); F[m + 1] = lds32(fa + 32 * m + 32);
#pragma unroll
      for (int be = 15; be >= 12; be--) {
        const int de = 8 * be - s;
        float(&a)[4] = (be >= 14 && !(i & 1)) ? acc[be - 6] : acc[be];
        if (de >= 0 && be >= 14 && i == 2 * (15 - be)) mma0(a[0], a[1], a[2], a[3], q[0], q[1], q[2], q[3], F[2 * de + 1], F[2 * de]);
        else if (de >= 0) mma(a[0], a[1], a[2], a[3], q[0], q[1], q[2], q[3], F[2 * de + 1], F[2 * de]);
      }
    }
#pragma unroll
    for (int i = 0; i < 8; i++) acc[14 + (i >> 2)][i & 3] += acc[8 + (i >> 2)][i & 3];
    F[64] = lds32(fa + 32 * 64); F[65] = lds32(fa + 32 * 65);
#pragma unroll
    for (int i = 0; i < 6; i++) ldsm4(qd[i], qa + 128 * 11 - 16 * i);
    float T[5][4];
#pragma unroll
    for (int i = 0; i < 16; i++) T[i >> 2][i & 3] = acc[12 + (i >> 2)][i & 3];
    nb_sync(NB_YZ, 160);
    TS(46);
    uint32_t held[2];
#pragma unroll
    for (int be = 11; be >= 0; be--) {
      if (be & 1) SPLITN(be);
      const uint32_t qp = qa + 128 * be;
#pragma unroll
      for (int k = 4; k >= 1; k--) mmac(T[k], qd[0][0], qd[0][1], qd[0][2], qd[0][3], F[16 * k + 1], F[16 * k], T[k - 1]);
      if (be >= 4) mmac(T[0], qd[0][0], qd[0][1], qd[0][2], qd[0][3], F[1], F[0], acc[be]);
      else mma0(T[0][0], T[0][1], T[0][2], T[0][3], qd[0][0], qd[0][1], qd[0][2], qd[0][3], F[1], F[0]);
      ldsm4(qd[6], qp - 16 * 6);
      ldsm4(qd[7], qp - 16 * 7);
      if (be > 4 && be <= 10) {
        const uint4 v = lds128(st + 512 * (be - 1));
        acc[be - 1][0] = uf(v.x); acc[be - 1][1] = uf(v.y); acc[be - 1][2] = uf(v.z); acc[be - 1][3] = uf(v.w);
      }
#pragma unroll
      for (int i = 1; i < 8; i++) {
#pragma unroll
        for (int k = 3; k >= 0; k--)
          mma(T[k][0], T[k][1], T[k][2], T[k][3], qd[i][0], qd[i][1], qd[i][2], qd[i][3], F[16 * k + 2 * i + 1], F[16 * k + 2 * i]);
        if (i < 7 && be > 0) ldsm4(qd[i - 1], qp - 128 - 16 * (i - 1));
        if (i == 2) {
          const uint32_t w0 = pack_bf(T[4][0], T[4][1]), w1 = pack_bf(T[4][2], T[4][3]);
          if (be & 1) { held[0] = w0; held[1] = w1; }
          else st_x(ydst + (be + 4) * 16, nz(w0), w1, held[0], held[1]);
          if ((be & 3) == 3 && be < 11) nb_arrive(NB_Y + 2 + (be >> 2), 160);
        }
      }
    }
    if ((fu(T[0][0]) & fu(T[1][0]) & fu(T[2][0]) & fu(T[3][0])) == 0xffffffffu) sts32(st + 2048, 0);
    nb_arrive(NB_BDONE, 288);
    nb_arrive(NB_Y + 1, 160);
#pragma unroll
    for (int B = 1; B >= 0; B--)
      st_x(ydst + B * 32, nz(pack_bf(T[2 * B][0], T[2 * B][1])), pack_bf(T[2 * B][2], T[2 * B][3]),
           pack_bf(T[2 * B + 1][0], T[2 * B + 1][1]), pack_bf(T[2 * B + 1][2], T[2 * B + 1][3]));
  }
}

__device__ __forceinline__ void dual_exp(const uint32_t* w, uint32_t* e) {
  const float L = 1.44268798828125f;
  uint32_t mx = bmax2(bmax2(w[0], w[1]), bmax2(w[2], w[3]));
  uint32_t mn = bmin2(bmin2(w[0], w[1]), bmin2(w[2], w[3]));
  mx = bmax2(mx, __shfl_xor_sync(0xffffffffu, mx, 1));
  mn = bmin2(mn, __shfl_xor_sync(0xffffffffu, mn, 1));
  mx = bmax2(mx, __shfl_xor_sync(0xffffffffu, mx, 2));
  mn = bmin2(mn, __shfl_xor_sync(0xffffffffu, mn, 2));
  const float mx0 = bf_lo(mx) * -L, mx1 = bf_hi(mx) * -L, mn0 = bf_lo(mn) * L, mn1 = bf_hi(mn) * L;
#pragma unroll
  for (int i = 0; i < 2; i++) {
    const float a0 = bf_lo(w[2 * i]), a1 = bf_hi(w[2 * i]), b0 = bf_lo(w[2 * i + 1]), b1 = bf_hi(w[2 * i + 1]);
    e[2 * i] = pack_bf(ex2(fmaf(a0, L, mx0)), ex2(fmaf(b0, L, mx0)));
    e[2 * i + 1] = pack_bf(ex2(fmaf(a1, L, mx1)), ex2(fmaf(b1, L, mx1)));
    e[4 + 2 * i] = pack_bf(ex2(fmaf(a0, -L, mn0)), ex2(fmaf(b0, -L, mn0)));
    e[5 + 2 * i] = pack_bf(ex2(fmaf(a1, -L, mn1)), ex2(fmaf(b1, -L, mn1)));
  }
}
__device__ __forceinline__ void normalise(uint32_t* e, const float (&s)[4]) {
  const uint32_t r = pack_bf(rcp(s[0]), rcp(s[2]));
  const __nv_bfloat162 rr = *(const __nv_bfloat162*)&r;
#pragma unroll
  for (int i = 0; i < 4; i++) {
    const __nv_bfloat162 v = __hmul2(*(const __nv_bfloat162*)&e[i], (i & 1) ? __high2bfloat162(rr) : __low2bfloat162(rr));
    e[i] = *(const uint32_t*)&v;
  }
}
__host__ __device__ constexpr uint64_t qdesc(uint32_t addr) { return mkdesc(addr, 128, 256, 0); }

__global__ void __launch_bounds__(NTHREADS, 1)
fused_kernel(const Params P, const __grid_constant__ CUtensorMap mx, const __grid_constant__ CUtensorMap mw,
             const __grid_constant__ CUtensorMap mo, const __grid_constant__ CUtensorMap mu,
             const __grid_constant__ CUtensorMap mout) {
  constexpr uint32_t sb = SB;
  const int tid = threadIdx.x, lane = tid & 31;
  const int warp = __shfl_sync(0xffffffffu, tid >> 5, 0);
  const int b = blockIdx.x, oct = b >> 3, i8 = b & 7;
  const int rt = (((oct & 4) ? ~oct : oct) & 3) * 2 + (i8 >> 2);
  const int hp = (oct >> 2) * 4 + (i8 & 3);

  const int wg = warp >> 2, w = warp & 3;
  const int d = b * 4 + ((tid >> 5) & 3);
  const KgenRaw raw = kgen_load(P, d, (tid >> 7) & 1, lane, (tid + 128) & 256);
  const uint32_t tb = sb + OFF_T + w * T_CH;
  if (warp >= 12) asm volatile("setmaxnreg.dec.sync.aligned.u32 32;");
  if (warp == 14) {
    asm volatile("prefetch.tensormap [%0];" ::"l"(&mw) : "memory");
    asm volatile("prefetch.tensormap [%0];" ::"l"(&mx) : "memory");
    asm volatile("prefetch.tensormap [%0];" ::"l"(&mu) : "memory");
  }
  if (warp == 12) {
    if (lane == 0) {
#pragma unroll
      for (int i = 0; i < 9; i++) mbar_init(BAR(i), 1);
      asm volatile("fence.mbarrier_init.release.cluster;" ::: "memory");
    }
    __syncwarp();
    if (lane < 9) mbar_expect(BAR(0) + 8 * lane, lane == 0 ? 16384 : 28672);
    __syncwarp();
    nb_arrive(NB_PROD, 384);
#pragma unroll 1
    for (int kb = 0; kb < 8; kb++) {
      if (kb == U_AT) e_tma4d(sb + OFF_STG0, &mu, BAR(MB_URAW), i8 * 64, oct * 2);
      e_tma3d(sb + OFF_W + kb * 12288, &mw, BAR(MB_FULL) + 8 * kb, hp * 32, kb * 64, 0);
      if (kb < 5) e_tma2d(sb + OFF_X + (kb < 2 ? kb + 3 : kb - 2) * 16384, &mx, BAR(MB_FULL) + 8 * kb, kb * 64, rt * 256);
    }
    if (smem_u32(smem_raw) != SB) __trap();
    if (lane == 0) TS1(54);
  }
  if (warp >= 12) {
    if (warp == 12) {
      nb_sync(NB_GATE + 1, 64);
      uint32_t slot = sb + OFF_X + 3 * 16384;
#pragma unroll 1
      for (int n = 0; n < 11; n++) {
        mbar_spin(BAR(MB_EMPTY) + 8 * n);
        const int m = n + 5;
        e_tma2d(slot, &mx, BAR(MB_FULL) + 8 * m, (m & 7) * 64, rt * 256 + (m >> 3) * 128);
        slot = slot == sb + OFF_X + 4 * 16384 ? sb + OFF_X : slot + 16384;
        if (n == 0) e_prefetch(P.x + (size_t)(rt * 256 + 128 + hp * 8) * 512, 8192);
        if (n == 7) {
          e_prefetch(P.wo + (size_t)b * 2048, 4096);
          asm volatile("prefetch.tensormap [%0];" ::"l"(&mo) : "memory");
          asm volatile("prefetch.tensormap [%0];" ::"l"(&mout) : "memory");
        }
      }
#pragma unroll 1
      for (int i = 0; i < 8; i++) {
        mbar_wait(BAR(MB_EMPTY + 10) + 8 * ((0x54332222u >> (4 * i)) & 7));
        const int w0 = (0x54736210u >> (4 * i)) & 7;
        e_tma3d(sb + OFF_W + w0 * 16384, &mo, BAR(MB_WO), 0, w0 * 64, (hp & 3) * 2);
      }
    } else {
      if (warp == 13) {
        if (lane == 0) {
#pragma unroll
          for (int i = 9; i < 40; i++) mbar_init(BAR(i), i < MB_EMPTY ? 1 : 4);
          asm volatile("fence.mbarrier_init.release.cluster;" ::: "memory");
        }
        __syncwarp();
        if (lane < 14 && lane != 9) mbar_expect(BAR(MB_FULL + 8) + 8 * lane, lane == 8 ? 131072 : (lane == 10 ? 8192 : (lane == 13 ? 24576 : 16384)));
        nb_arrive(NB_GATE + 1, 64);
      } else if (warp == 14) {
        e_prefetch(P.x + (size_t)(rt * 256 + hp * 8) * 512, 8192);
      }
      nb_sync(NB_PROD, 384);
      if (warp == 15) {
        const uint4 v0 = __ldg((const uint4*)P.wphi + hp * 64 + lane), v1 = __ldg((const uint4*)P.wphi + hp * 64 + 32 + lane);
        sts128(sb + OFF_PHI + (lane & 1) * 256 + (lane >> 1) * 16, v0.x, v0.y, v0.z, v0.w);
        sts128(sb + OFF_PHI + 512 + (lane & 1) * 256 + (lane >> 1) * 16, v1.x, v1.y, v1.z, v1.w);
        const uint32_t one = (((lane >> 3) ^ (lane >> 4)) & 1) ? 0u : ((lane & 1) ? 0x3F800000u : 0x3F80u);
        const int q = (lane >> 1) & 3;
        sts128(sb + OFF_EYE + lane * 16, q == 0 ? one : 0u, q == 1 ? one : 0u, q == 2 ? one : 0u, q == 3 ? one : 0u);
        sts64(sb + OFF_ONE + lane * 8, 0x3F803F80u, 0x3F803F80u);
        asm volatile("fence.proxy.async.shared::cta;" ::: "memory");
        nb_arrive(NB_KREAD, 160);
      }
      uint32_t* cnt = (uint32_t*)(P.xs + X_CNT) + (warp == 13 ? i8 : (warp == 14 ? 8 + rt : 16 + oct)) * 32;
      const unsigned target = (ld_x32(cnt) & ~15u) + 16;
      if (warp != 14) {
        if (warp == 15) mbar_wait(BAR(MB_EMPTY + ZERO_STEP));
        uint4* pz = P.xs + (warp == 13 ? X_PART + (hp * 8 + rt) * 144 : X_Y + b * 1024) + lane;
#pragma unroll 1
        for (int i = (warp == 13 ? 144 : 1024) - lane; i > 0; i -= 32, pz += 32) st_x(pz, 0, 0, 0, 0);
      }
      if (warp == 15) __syncwarp();
      else nb_sync(warp == 13 ? NB_INIT : NB_ODONE, warp == 13 ? 160 : 288);
      if (lane == 0) asm volatile("red.release.gpu.global.add.u32 [%0], %1;" ::"l"(cnt), "r"(warp == 15 ? 2 : 1) : "memory");
      if (lane == 0) TS1(warp == 13 ? 50 : (warp == 14 ? 57 : 53));
      __syncwarp();
      if (warp == 14) nb_arrive(NB_GATE + 1, 160);
      asm volatile("fence.proxy.async.shared::cta;" ::: "memory");
      if (warp == 13) cnt += ((lane & 1 ? b >> 4 : i8 ^ (lane & 4)) - i8) * 32;
#pragma unroll 1
      for (int i = 0; i < SPIN_MAX; i++) {
        unsigned v;
        asm volatile("ld.acquire.gpu.global.u32 %0, [%1];" : "=r"(v) : "l"(cnt) : "memory");
        if (__all_sync(0xffffffffu, (int)(v - target) >= 0)) break;
      }
      if (lane == 0) TS1(warp == 13 ? 51 : (warp == 14 ? 58 : 55));
      if (warp == 15) { nb_arrive(NB_YZ, 160); return; }
      asm volatile("fence.proxy.async.global;" ::: "memory");
      if (warp == 13) {
        mbar_wait(BAR(MB_EMPTY + 11));
        e_expect(BAR(MB_UFULL), 4 * U_CH);
        e_bulk(sb + OFF_U, P.xs + X_UT + b * (U_CH / 4), 4 * U_CH, BAR(MB_UFULL));
      } else {
        const uint4* src = P.xs + X_O + (rt * 4 + (hp >> 2)) * 4096;
        e_bulk(sb + OFF_X + 32768 + 57344, src + 3584, 8192, BAR(MB_O));
        e_bulk(sb + OFF_X + 32768, src, 16384, BAR(MB_O + 1));
        e_bulk(sb + OFF_X + 49152, src + 1024, 16384, BAR(MB_O + 2));
        e_bulk(sb + OFF_STG0, src + 3200, 6144, BAR(MB_O + 3));
        nb_sync(NB_BDONE, 288);
        asm volatile("fence.proxy.async.shared::cta;" ::: "memory");
        e_bulk(sb + OFF_U, src + 2048, 18432, BAR(MB_O + 3));
      }
    }
    return;
  }

  asm volatile("setmaxnreg.inc.sync.aligned.u32 160;");
  const int t = tid & 127;
  const int g = lane >> 2, c = lane & 3;
  const uint32_t kp = ((tb + 127) & ~127u) + (wg & 1) * 2048;
  const KgenAddr kad = kgen_addr(lane, kp);
  if (wg) nb_sync(NB_PROD, 384);
  SPLIT();
  float k[5][4], k2048, ksc;
  if (wg) {
    kgen_unit(raw, kad, blockIdx.y, k, k2048, ksc);
    TS(40 + wg);
    if ((fu(k[0][0]) & fu(k[1][0]) & fu(k[2][0]) & fu(k[3][0]) & fu(k[4][0])) == 0xffffffffu) sts32(kp, 0);
  }
  if (wg) nb_arrive(0, 384);
  if (wg) {
    if (wg == 1) {
      uint32_t h[10];
#pragma unroll
      for (int j = 0; j < 10; j++) h[j] = hu(__floats2half2_rn(k[j >> 1][2 * (j & 1)], k[j >> 1][2 * (j & 1) + 1]));
      sts128(kp + lane * 16, h[0], h[1], h[2], h[3]);
      sts128(kp + 512 + lane * 16, h[4], h[5], h[6], h[7]);
      sts128(kp + 1024 + lane * 16, h[8], h[9], fu(k2048), fu(ksc));
      nb_arrive(NB_PREP, 256);
    }
  } else {
    nb_sync(NB_KREAD, 160);
  }
  if (wg == 1) {
    mbar_wait(BAR(MB_URAW));
    TS(48);
    uint4* dst = P.xs + X_UT + (i8 * 64 + g) * (U_CH / 16) + (w & 1) * (U_ODD / 16) + U_PAD / 16 + oct * 8 + (w >> 1) * 4 + c;
    const int ln = ((lane >> 1) & 3) + 4 * (lane & 1);
    uint32_t r[8][4];
#pragma unroll
    for (int i = 0; i < 8; i++) ldsm4t(r[i], sb + OFF_STG0 + w * 4096 + ((lane >> 3) * 8 + ln) * 128 + ((i ^ ln) << 4));
#pragma unroll
    for (int i = 0; i < 8; i++) dst[i * (U_CH / 2)] = make_uint4(r[i][0], r[i][1], r[i][2], r[i][3]);
    nb_arrive(NB_INIT, 160);
    if (lane == 0) mbar_arrive(BAR(MB_AUX));
  }
  {
    if (wg == 2) {
#pragma unroll
      for (int j = 0; j < 5; j++) { k[j][0] *= ksc; k[j][1] *= ksc; k[j][2] *= ksc; k[j][3] *= ksc; }
      const unsigned short dsk = __ldg((const unsigned short*)P.Dskip + d);
      nb_sync(NB_PREP, 256);
      {
        const uint32_t src = kp + 2048 + lane * 16;
        const uint4 v0 = lds128(src), v1 = lds128(src + 512), v2 = lds128(src + 1024);
        const uint32_t h[10] = {v0.x, v0.y, v0.z, v0.w, v1.x, v1.y, v1.z, v1.w, v2.x, v2.y};
#pragma unroll
        for (int j = 0; j < 10; j++) {
          const float2 f = __half22float2(*(const __half2*)&h[j]);
          k[j >> 1][2 * (j & 1)] = fmaf(f.x, uf(v2.w), k[j >> 1][2 * (j & 1)]);
          k[j >> 1][2 * (j & 1) + 1] = fmaf(f.y, uf(v2.w), k[j >> 1][2 * (j & 1) + 1]);
        }
        k2048 += uf(v2.z);
      }
#pragma unroll
      for (int o2 = 16; o2; o2 >>= 1) k2048 += __shfl_xor_sync(0xffffffffu, k2048, o2);
      if (lane == 0) k[0][0] += bf_lo(dsk);
      __syncwarp();
      TS(34);
      build_tables(tb, lane, k, k2048);
      TS(35);
      uint4* const g_y = P.xs + X_Y;
      conv_channel(sb + OFF_U + w * U_CH, tb, lane, g_y + (size_t)d * 256 + lane);
      nb_arrive(NB_Y, 160);
      TS(37);
      if (w == 0) TSDUMP(32);
      return;
    }
    if (wg == 1) {
      mbar_wait(BAR(MB_EMPTY + 4));
      mbar_spin(BAR(MB_EMPTY + 6));
    }
    TS(wg * 16 + 1);
  }

  float acc[2][48];
  {
    uint32_t fb = BAR(MB_FULL) + 64 * wg;
    uint32_t da = (uint32_t)mkdesc(sb + OFF_X, 16, 0, 0) + (wg ? 1024 : 3072), db = (uint32_t)mkdesc(sb + OFF_W, 4096, 0, 0);
    constexpr uint64_t ha = mkdesc(0, 0, 1024, 1), hb = mkdesc(0, 0, 512, 2);
    mbar_spin(fb);
    if (wg == 0) nb_sync(0, 384);
    TS(wg * 16 + 2);
#pragma unroll 1
    for (int kb = 0; kb < 8; kb++) {
      const uint32_t ready = mbar_test(kb < 7 ? fb + 8 : fb);
      WG_FENCE();
#pragma unroll
      for (int k = 0; k < 4; k++) {
        wgmma_ss_n96(acc[0], ha | (da + 2 * k), hb | (db + 64 * k), k ? 1 : kb);
        wgmma_ss_n96(acc[1], ha | (da + 2 * k + 512), hb | (db + 64 * k), k ? 1 : kb);
      }
      WG_COMMIT();
      WG_WAIT(1);
      if (kb > 0) e_arrive(fb + 8 * (MB_EMPTY - MB_FULL - 1));
      if (!ready) mbar_spin(fb + 8);
      fb += 8; db += 768;
      da = da == (uint32_t)mkdesc(sb + OFF_X + 65536, 16, 0, 0) ? da - 4096 : da + 1024;
    }
    WG_WAIT(0);
    e_arrive(fb + 8 * (MB_EMPTY - MB_FULL - 1));
    SPLIT();
  }
  TS(wg * 16 + 3);

  constexpr uint32_t stg0 = sb + OFF_STG0, stg1 = sb + OFF_X + 32768;
  uint4* const g_part = P.xs + X_PART;
  uint4* const g_o = P.xs + X_O;
  constexpr uint32_t kvs = stg0;
  auto pack8 = [](const float* a) { return make_uint4(pack_bf(a[0], a[1]), pack_bf(a[2], a[3]), pack_bf(a[4], a[5]), pack_bf(a[6], a[7])); };
  auto stage_k = [&](auto nt, const uint4* af, const uint4* vp, uint32_t sl, uint32_t free_bar) {
    constexpr int NU = 2 * decltype(nt)::value;
    float p[NU][8], rs[2 * NU][4];
    uint32_t ek[8 * NU];
    WG_FENCE();
#pragma unroll
    for (int u = 0; u < NU; u++) wgmma_rs_n16(p[u], af[u], qdesc(sb + OFF_PHI + (u & 1) * 512), 0);
    WG_COMMIT();
    WG_WAIT(0);
#pragma unroll
    for (int u = 0; u < NU; u++) {
      const uint32_t pw[4] = {pack_bf(p[u][0], p[u][2]), pack_bf(p[u][1], p[u][3]), pack_bf(p[u][4], p[u][6]), pack_bf(p[u][5], p[u][7])};
      dual_exp(pw, ek + 8 * u);
    }
    TS(wg * 16 + 12);
    mbar_spin(free_bar);
    WG_FENCE();
#pragma unroll
    for (int i = 0; i < 2 * NU; i++) wgmma_rs_n8(rs[i], make_uint4(ek[4 * i], ek[4 * i + 1], ek[4 * i + 2], ek[4 * i + 3]), qdesc(sb + OFF_ONE), 0);
    WG_COMMIT();
#pragma unroll
    for (int i = 0; i < NU; i++) stsm4(sl + (i >> 1) * 4 * SLAB + 2048 + (i & 1) * 512, vp[i].x, vp[i].y, vp[i].z, vp[i].w);
    if (NU == 4 || lane < 16) sts128(sl + (lane >> 4) * (4 * SLAB - 256) + 3072, 0x3F803F80u, 0x3F803F80u, 0x3F803F80u, 0x3F803F80u);
    WG_WAIT(0);
#pragma unroll
    for (int i = 0; i < 2 * NU; i++) {
      normalise(ek + 4 * i, rs[i]);
      stsm4(sl + (i >> 2) * 4 * SLAB + (i & 3) * 512, ek[4 * i], ek[4 * i + 1], ek[4 * i + 2], ek[4 * i + 3]);
    }
    asm volatile("fence.proxy.async.shared::cta;" ::: "memory");
  };
  auto contract = [&](float (&kc)[20], uint32_t stg, int acc_in) {
    WG_FENCE();
#pragma unroll
    for (int s = 0; s < 8; s++) wgmma_ss_n40(kc, qdesc(stg + s * SLAB), qdesc(stg + s * SLAB + 2048), s ? 1 : acc_in);
    WG_COMMIT();
    WG_WAIT(0);
  };
  uint32_t eq[32];
  {
    uint4 af[4], aq[4], vp[4];
    float kc[20];
#pragma unroll
    for (int u = 0; u < 4; u++) { af[u] = pack8(acc[u >> 1] + 16 + 8 * (u & 1)); vp[u] = pack8(acc[u >> 1] + 32 + 8 * (u & 1)); }
    const uint32_t hand = stg1 + 16384 + 8192 + w * 2048 + lane * 16;
    if (wg) {
      sts128(hand, af[2].x, af[2].y, af[2].z, af[2].w); sts128(hand + 512, af[3].x, af[3].y, af[3].z, af[3].w);
      sts128(hand + 1024, vp[2].x, vp[2].y, vp[2].z, vp[2].w); sts128(hand + 1536, vp[3].x, vp[3].y, vp[3].z, vp[3].w);
      nb_arrive(NB_HAND, 256);
    }
#pragma unroll
    for (int u = 0; u < 4; u++) aq[u] = pack8(acc[u >> 1] + 8 * (u & 1));
    if (wg == 0) {
      stage_k(std::integral_constant<int, 2>(), af, vp, stg0 + w * SLAB + lane * 16, BAR(MB_AUX));
      TS(13);
      nb_sync(NB_WG0, 128);
      contract(kc, stg0, 0);
      mbar_wait(BAR(MB_UFULL));
      TS(15);
      nb_sync(NB_HAND, 256);
      af[0] = lds128(hand); af[1] = lds128(hand + 512); vp[0] = lds128(hand + 1024); vp[1] = lds128(hand + 1536);
      nb_sync(NB_WG0, 128);
    }
    stage_k(std::integral_constant<int, 1>(), af, vp, stg1 + (wg ? w : 4 + w) * SLAB + lane * 16, BAR(MB_EMPTY + 15));
    TS(wg * 16 + 14);
    float p[4][8];
    if (wg) {
      nb_arrive(NB_ST0, 256);
      nb_arrive(NB_GATE, 256);
    } else {
      uint4* pp = g_part + (size_t)(hp * 8 + rt) * 144 + t;
      uint32_t* pz = (uint32_t*)(pp - t + 128) + w * 16 + c * 8 + g;
      asm volatile("" : "+l"(pp), "+l"(pz));
      nb_sync(NB_ST0, 256);
      contract(kc, stg1, 1);
      TS(6);
      float kv[8];
#pragma unroll
      for (int i = 0; i < 8; i++) kv[i] = w & 2 ? kc[8 + i] : kc[i];
      st_x(pp, nz(pack_bf(kv[0], kv[1])), pack_bf(kv[2], kv[3]), pack_bf(kv[4], kv[5]), pack_bf(kv[6], kv[7]));
      if (c < 2) st_x32(pz, nz(fu(c ? kc[18] : kc[16])));
      TS(5);
    }
    SPLIT();
    WG_FENCE();
#pragma unroll
    for (int u = 0; u < 4; u++) wgmma_rs_n16(p[u], aq[u], qdesc(sb + OFF_PHI + (u & 1) * 512), 0);
    WG_COMMIT();
    WG_WAIT(0);
#pragma unroll
    for (int u = 0; u < 4; u++) {
      const uint32_t pw[4] = {pack_bf(p[u][0], p[u][2]), pack_bf(p[u][1], p[u][3]), pack_bf(p[u][4], p[u][6]), pack_bf(p[u][5], p[u][7])};
      dual_exp(pw, eq + 8 * u);
    }
    SPLIT();
  }
  TS(wg * 16 + 4);
  if (wg == 1) {
    mbar_wait(BAR(MB_UFULL));
    const uint4* ps = g_part + (size_t)hp * 8 * 144 + t;
    const uint32_t* zs = (const uint32_t*)(g_part + (size_t)(hp * 8 + (lane >> 4) * 4) * 144 + 128) + w * 16 + (lane & 15);
    uint4 v[8];
    uint32_t zv[4];
#pragma unroll 1
    for (int it = 0; it < SPIN_MAX; it++) {
#pragma unroll
      for (int i = 0; i < 8; i++) v[i] = ld_x(ps + i * 144);
#pragma unroll
      for (int i = 0; i < 4; i++) zv[i] = ld_x32(zs + i * 576);
      uint32_t m = min(min(zv[0], zv[1]), min(zv[2], zv[3]));
#pragma unroll
      for (int i = 0; i < 8; i++) m = min(m, v[i].x);
      if (__all_sync(0xffffffffu, m != 0)) break;
    }
    float s[8];
    WG_FENCE();
#pragma unroll
    for (int r = 0; r < 8; r++) wgmma_rs_n16(s, v[r], qdesc(sb + OFF_EYE), r);
    WG_COMMIT();
    float zsum = (uf(zv[0]) + uf(zv[1])) + (uf(zv[2]) + uf(zv[3]));
    zsum += __shfl_xor_sync(0xffffffffu, zsum, 16);
    const uint32_t z1 = pack_bf(zsum, 1.f);
    if (lane < 16) sts128(kvs + w * 768 + 512 + lane * 16, z1, z1, z1, z1);
    WG_WAIT(0);
    stsm4(kvs + w * 768 + lane * 16, pack_bf(s[0], s[1]), pack_bf(s[2], s[3]), pack_bf(s[4], s[5]), pack_bf(s[6], s[7]));
    asm volatile("fence.proxy.async.shared::cta;" ::: "memory");
    TS(22);
  }
  nb_sync(NB_KV, 256);
  {
    float n[8][12];
    WG_FENCE();
#pragma unroll
    for (int i = 0; i < 8; i++) wgmma_rs_n24(n[i], make_uint4(eq[4 * i], eq[4 * i + 1], eq[4 * i + 2], eq[4 * i + 3]), qdesc(kvs + (i & 3) * 768), 0);
    WG_COMMIT();
    uint32_t* od = (uint32_t*)(g_o + (size_t)((rt * 4 + wg * 2) * 32 + hp * 2) * 128) + w * 64 + lane;
    WG_WAIT(0);
#pragma unroll
    for (int u = 0; u < 4; u++) {
      float(&np)[12] = n[2 * u];
      const float(&nm)[12] = n[2 * u + 1];
      const float q0 = np[9] * rcp(nm[9]), q1 = np[11] * rcp(nm[11]);
      const float r0 = rcp(fmaf(nm[8], q0, fmaf(np[9], 1e-6f, np[8]))), r1 = rcp(fmaf(nm[10], q1, fmaf(np[11], 1e-6f, np[10])));
#pragma unroll
      for (int i = 0; i < 8; i++) np[i] = fmaf(nm[i], (i & 2) ? q1 : q0, np[i]);
      uint32_t* o = od + (u >> 1) * 16384 + (u & 1) * 512;
      o[0] = pack_bf(np[0] * r0, np[1] * r0);
      o[32] = pack_bf(np[2] * r1, np[3] * r1);
      o[256] = pack_bf(np[4] * r0, np[5] * r0);
      o[288] = pack_bf(np[6] * r1, np[7] * r1);
      if (u == 1) SPLIT();
    }
  }
  TS(wg * 16 + 7);
  nb_arrive(NB_ODONE, 288);
  if (wg) {
    const uint4* src = P.xs + X_Y + (oct * 32 + c * 8) * 256 + (2 * w + (g >> 2)) * 32 + i8 * 4 + (g & 3);
    __nv_bfloat16* dst = P.out + (size_t)((2 * w + (g >> 2)) * 256 + i8 * 16 + (g & 3) * 2) * 1024 + 512 + oct * 32 + c * 8;
    nb_sync(NB_GATE + 1, 160);
    nb_sync(NB_Y + w, 160);
    uint4 v[8];
#pragma unroll 1
    for (int it = 0; it < SPIN_MAX; it++) {
      uint32_t m = 0xffffffffu;
#pragma unroll
      for (int i = 0; i < 8; i++) v[i] = ld_x(src + i * 256);
#pragma unroll
      for (int i = 0; i < 8; i++) m = min(m, v[i].x);
      if (__all_sync(0xffffffffu, m != 0)) break;
    }
#pragma unroll
    for (int i = 0; i < 8; i++) *(uint4*)(dst + (size_t)((i >> 2) * 128 + ((i >> 1) & 1) * 8 + (i & 1)) * 1024) = tr_row(v, i);
    TS(31);
    GT(63);
    if (w == 0) TSDUMP(16);
    return;
  }
  mbar_wait(BAR(MB_WO));
  nb_sync(NB_BDONE, 288);
  TS(8);
  mbar_spin(BAR(MB_O));
  TS(9);
  constexpr uint64_t ha = mkdesc(0, 0, 128, 0), hb = mkdesc(0, 0, 1024, 1);
  constexpr uint32_t da0 = (uint32_t)mkdesc(stg1, 1024, 0, 0), db0 = (uint32_t)mkdesc(sb + OFF_W, 8192, 0, 0);
  const uint32_t ot = ((sb + OFF_T + 1023) & ~1023u) + w * 4096;
  auto store_half = [&](const float* oc, int hf) {
#pragma unroll
    for (int i = 0; i < 8; i += 2)
      stsm4(ot + hf * 2048 + (lane & 15) * 128 + (((i + (lane >> 4)) ^ lane) & 7) * 16, pack_bf(oc[4 * i], oc[4 * i + 1]),
            pack_bf(oc[4 * i + 2], oc[4 * i + 3]), pack_bf(oc[4 * i + 4], oc[4 * i + 5]), pack_bf(oc[4 * i + 6], oc[4 * i + 7]));
    asm volatile("fence.proxy.async.shared::cta;" ::: "memory");
    __syncwarp();
    e_store2d(&mout, ot + hf * 2048, (hp & 3) * 128 + hf * 64, (rt * 4 + (hp >> 2)) * 64 + w * 16);
  };
  float oc[64];
#pragma unroll 1
  for (int j = 0; j < 8; j++) {
    const int kb = (j + 7) & 7;
    if ((j & 1) && j < 6) mbar_spin(BAR(MB_O + 1) + 4 * (j - 1));
    WG_FENCE();
#pragma unroll
    for (int k = 0; k < 4; k++) wgmma_ss_n128(oc, ha | (da0 + 512 * kb + 128 * k), hb | (db0 + 1024 * kb + 128 * k), k ? 1 : j);
    WG_COMMIT();
  }
  WG_WAIT(0);
  TS(10);
  store_half(oc, 0);
  store_half(oc + 32, 1);
  asm volatile(ELECT "cp.async.bulk.commit_group;\n@p cp.async.bulk.wait_group.read 0;\n}\n" ::: "memory");
  TS(wg * 16 + 11);
  GT(61 + wg);
  if (w == 0) TSDUMP(0);
  if (w == 1) TSDUMP(48);
}

typedef CUresult (*EncodeFn)(CUtensorMap*, CUtensorMapDataType, cuuint32_t, void*, const cuuint64_t*, const cuuint64_t*,
                             const cuuint32_t*, const cuuint32_t*, CUtensorMapInterleave, CUtensorMapSwizzle,
                             CUtensorMapL2promotion, CUtensorMapFloatOOBfill);

}

extern "C" void kernel_launch(void* const* d_in, const int* in_sizes, int n_in, void* d_out, int out_size) {
  (void)in_sizes; (void)n_in; (void)out_size;
  void* fn = nullptr;
  cudaDriverEntryPointQueryResult qr;
  cudaGetDriverEntryPoint("cuTensorMapEncodeTiled", &fn, cudaEnableDefault, &qr);
  EncodeFn enc = (EncodeFn)fn;
  CUtensorMap mx, mw, mo, mu, mout;
  const cuuint32_t es[5] = {1, 1, 1, 1, 1};
  {
    cuuint64_t dims[2] = {512, 2048}, st[1] = {1024};
    cuuint32_t box[2] = {64, 128};
    enc(&mx, CU_TENSOR_MAP_DATA_TYPE_BFLOAT16, 2, d_in[0], dims, st, box, es, CU_TENSOR_MAP_INTERLEAVE_NONE,
        CU_TENSOR_MAP_SWIZZLE_128B, CU_TENSOR_MAP_L2_PROMOTION_L2_128B, CU_TENSOR_MAP_FLOAT_OOB_FILL_NONE);
  }
  {
    cuuint64_t dims[3] = {512, 512, 3}, st[2] = {3072, 1024};
    cuuint32_t box[3] = {32, 64, 3};
    enc(&mw, CU_TENSOR_MAP_DATA_TYPE_BFLOAT16, 3, d_in[1], dims, st, box, es, CU_TENSOR_MAP_INTERLEAVE_NONE,
        CU_TENSOR_MAP_SWIZZLE_64B, CU_TENSOR_MAP_L2_PROMOTION_L2_128B, CU_TENSOR_MAP_FLOAT_OOB_FILL_NONE);
  }
  {
    cuuint64_t dims[3] = {64, 512, 8}, st[2] = {1024, 128};
    cuuint32_t box[3] = {64, 64, 2};
    enc(&mo, CU_TENSOR_MAP_DATA_TYPE_BFLOAT16, 3, d_in[3], dims, st, box, es, CU_TENSOR_MAP_INTERLEAVE_NONE,
        CU_TENSOR_MAP_SWIZZLE_128B, CU_TENSOR_MAP_L2_PROMOTION_L2_128B, CU_TENSOR_MAP_FLOAT_OOB_FILL_NONE);
  }
  {
    cuuint64_t dims[4] = {512, 4, 16, 32}, st[3] = {16384, 1024, 65536};
    cuuint32_t box[4] = {64, 4, 16, 2};
    enc(&mu, CU_TENSOR_MAP_DATA_TYPE_BFLOAT16, 4, d_in[4], dims, st, box, es, CU_TENSOR_MAP_INTERLEAVE_NONE,
        CU_TENSOR_MAP_SWIZZLE_128B, CU_TENSOR_MAP_L2_PROMOTION_L2_128B, CU_TENSOR_MAP_FLOAT_OOB_FILL_NONE);
  }
  {
    cuuint64_t dims[2] = {1024, 2048}, st[1] = {2048};
    cuuint32_t box[2] = {64, 16};
    enc(&mout, CU_TENSOR_MAP_DATA_TYPE_BFLOAT16, 2, d_out, dims, st, box, es, CU_TENSOR_MAP_INTERLEAVE_NONE,
        CU_TENSOR_MAP_SWIZZLE_128B, CU_TENSOR_MAP_L2_PROMOTION_NONE, CU_TENSOR_MAP_FLOAT_OOB_FILL_NONE);
  }
  Params P;
  P.x = (const __nv_bfloat16*)d_in[0];
  P.wphi = (const __nv_bfloat16*)d_in[2];
  P.wo = (const __nv_bfloat16*)d_in[3];
  P.logA = (const __nv_bfloat16*)d_in[5];
  P.Aim = (const __nv_bfloat16*)d_in[6];
  P.Cre = (const __nv_bfloat16*)d_in[7];
  P.Cim = (const __nv_bfloat16*)d_in[8];
  P.logdt = (const __nv_bfloat16*)d_in[9];
  P.Dskip = (const __nv_bfloat16*)d_in[10];
  P.out = (__nv_bfloat16*)d_out;
  cudaGetSymbolAddress((void**)&P.xs, g_x);
  P.ts = nullptr;
  cudaFuncSetAttribute(fused_kernel, cudaFuncAttributeMaxDynamicSharedMemorySize, SMEM_BYTES);
  fused_kernel<<<NCTA, NTHREADS, SMEM_BYTES>>>(P, mx, mw, mo, mu, mout);
}
```
